```python
import torch

def _softmax(x, axis=-1):
    return torch.softmax(x, dim=axis)
def _gelu(x):
    return torch.nn.functional.gelu(x, approximate="tanh")
def _silu(x):
    return torch.nn.functional.silu(x)
def _sigmoid(x):
    return torch.sigmoid(x)
def _layernorm(x, axis=-1, eps=1e-5):
    m = x.mean(dim=axis, keepdim=True)
    v = x.var(dim=axis, keepdim=True, unbiased=False)
    return (x - m) / torch.sqrt(v + eps)
def _scatter_add(tgt, idx, src, axis=0):
    return tgt.clone().index_add_(axis, idx, src)
def _segment_sum(src, seg, n):
    out = torch.zeros((n,) + src.shape[1:], dtype=src.dtype)
    return out.index_add_(0, seg, src)
def _pad(x, pw):
    flat = tuple(v for pair in reversed(pw) for v in pair)
    return torch.nn.functional.pad(x, flat)

kernel_name = 'gated_mix__spectral_gfnet__glu_gated_reglu__prompt'

def setup_inputs():

    _w = (lambda a: (lambda t: t.to(torch.bfloat16) if t.is_floating_point() else t)(torch.as_tensor(a)))
    def _A_setup():
        B, S, D = 1, 2048, 512
        Df = D // 2 + 1
        return {
            "x": _w((lambda *s: torch.randn(*s, dtype=torch.bfloat16) * 0.05)(B, S, D)),
            "w_r": _w((lambda *s: torch.randn(*s, dtype=torch.bfloat16) * 0.05)(S, Df) * 0.02),
            "w_i": _w((lambda *s: torch.randn(*s, dtype=torch.bfloat16) * 0.05)(S, Df) * 0.02),
        }
    _A_in = _A_setup()

    def _B_setup():
        B, S, D, F = 1, 2048, 512, 1792
        return {
            "x": _w((lambda *s: torch.randn(*s, dtype=torch.bfloat16) * 0.05)(B, S, D)),
            "W_gate": _w((lambda *s: torch.randn(*s, dtype=torch.bfloat16) * 0.2)(D, F) * (2.0 / D) ** 0.5),
            "W_up": _w((lambda *s: torch.randn(*s, dtype=torch.bfloat16) * 0.2)(D, F) * (2.0 / D) ** 0.5),
            "W_down": _w((lambda *s: torch.randn(*s, dtype=torch.bfloat16) * 0.2)(F, D) * (1.0 / F) ** 0.5),
        }
    _B_in = _B_setup()

    return {
        "A_x": _A_in["x"],
        "A_w_r": _A_in["w_r"],
        "A_w_i": _A_in["w_i"],
        "B_x": _B_in["x"],
        "B_W_gate": _B_in["W_gate"],
        "B_W_up": _B_in["W_up"],
        "B_W_down": _B_in["W_down"],
        "gate_w": _w((lambda *s: torch.randn(*s, dtype=torch.bfloat16) * 0.05)(512) * 16.0),
    }

def reference(A_x, A_w_r, A_w_i, B_x, B_W_gate, B_W_up, B_W_down, gate_w):
    def _A_ref(x, w_r, w_i):
        B, S, D = x.shape
        X = (lambda x, axes=(-2,-1): torch.fft.rfft2(x.float(), dim=axes))(x, axes=(-2, -1))
        W = w_r + 1j * w_i
        X = X * W
        y = (lambda x, s, axes=(-2,-1): torch.fft.irfft2(x, s=s, dim=axes).to(torch.bfloat16))(X, (S, D), axes=(-2, -1))
        return y

    def _B_ref(x, W_gate, W_up, W_down):
        gate = torch.einsum("bsd,df->bsf", x, W_gate)
        up = torch.einsum("bsd,df->bsf", x, W_up)
        gate = gate * (lambda x, dt: x.to(dt))(gate > 0, gate.dtype)
        h = gate * up
        return torch.einsum("bsf,fd->bsd", h, W_down)

    x = A_x
    g = _sigmoid((x * gate_w).sum(-1, keepdims=True))
    a = _A_ref(x, A_w_r, A_w_i)
    b = _B_ref(x, B_W_gate, B_W_up, B_W_down)
    return g * a + (1 - g) * b
```

```cpp
#include <cuda_runtime.h>
#include <cuda_bf16.h>
#include <cuda.h>
#include <stdint.h>

namespace tbl {
constexpr double PI = 3.14159265358979323846264338327950288;
constexpr double sin_s(double x) { double t = x, s = x; for (int n = 1; n < 12; n++) { t *= -x * x / ((2 * n) * (2 * n + 1)); s += t; } return s; }
constexpr double cos_s(double x) { double t = 1, s = 1; for (int n = 1; n < 12; n++) { t *= -x * x / ((2 * n - 1) * (2 * n)); s += t; } return s; }
constexpr double cos2048(int m) {
  m &= 2047; if (m > 1024) m = 2048 - m;
  bool neg = false; if (m > 512) { m = 1024 - m; neg = true; }
  double v = (m <= 256) ? cos_s(2 * PI * m / 2048) : sin_s(2 * PI * (512 - m) / 2048);
  return neg ? -v : v;
}
constexpr uint16_t to_bf16(double v) {
  if (v == 0) return 0;
  uint16_t s = 0; if (v < 0) { s = 0x8000; v = -v; }
  int e = 0; while (v >= 2) { v /= 2; e++; } while (v < 1) { v *= 2; e--; }
  double m = (v - 1) * 128; int mi = (int)m; double fr = m - mi;
  if (fr > 0.5 || (fr == 0.5 && (mi & 1))) mi++;
  if (mi == 128) { mi = 0; e++; }
  return (uint16_t)(s | ((e + 127) << 7) | mi);
}
struct CosT { uint16_t v[2048]; constexpr CosT() : v() { for (int i = 0; i < 2048; i++) v[i] = to_bf16(cos2048(i)); } };
struct alignas(1024) FT {
  uint16_t v[512 * 512];
  constexpr FT() : v() {
    CosT c;
    for (int r = 0; r < 512; r++) {
      int k = (r >> 4) * 8 + (r & 7), e = (r >> 3) & 1;
      int mul = 4 * k, add = e ? 512 : 0;
      if (k == 0 && e == 1) { mul = 1024; add = 0; }
      for (int d = 0; d < 512; d++) v[r * 512 + d] = c.v[(d * mul + add) & 2047];
    }
  }
};
struct alignas(1024) ET {
  uint16_t v[2048 * 128];
  constexpr ET() : v() {
    CosT c;
    for (int s = 0; s < 2048; s++)
      for (int j = 0; j < 64; j++) { v[s * 128 + j] = c.v[(s * j) & 2047]; v[s * 128 + 64 + j] = c.v[(s * j + 512) & 2047]; }
  }
};
template <int A> struct W32 {
  static constexpr float c = (float)cos2048(A * 64);
  static constexpr float s = (float)cos2048(A * 64 - 512);
};
}

__device__ constexpr tbl::FT g_FT = tbl::FT();
__device__ constexpr tbl::ET g_ET = tbl::ET();

__device__ __align__(1024) float2 g_X1p[128 * 32 * 128];
__device__ __align__(1024) float2 g_X1s[2 * 32 * 64];
__device__ __align__(1024) uint32_t g_Tp[32 * 64 * 256];
__device__ __align__(1024) uint4 g_part[16 * 8 * 8 * 1024];
__device__ unsigned g_ticket;
__device__ unsigned g_cntX[8 * 32];
__device__ unsigned g_cntT[8 * 32];
__device__ unsigned g_cntP[128 * 32];
#define PROF_EV(i) do {} while (0)
#define PROF_CK(i) do {} while (0)

__device__ __forceinline__ uint32_t smem_u32(const void* p) { return (uint32_t)__cvta_generic_to_shared(p); }
__device__ __forceinline__ void mbar_init(uint32_t bar, uint32_t cnt) { asm volatile("mbarrier.init.shared::cta.b64 [%0], %1;" ::"r"(bar), "r"(cnt)); }
__device__ __forceinline__ void mbar_expect_tx(uint32_t bar, uint32_t bytes) { asm volatile("mbarrier.arrive.expect_tx.shared::cta.b64 _, [%0], %1;" ::"r"(bar), "r"(bytes) : "memory"); }
__device__ __forceinline__ void mbar_arrive(uint32_t bar) { asm volatile("mbarrier.arrive.shared::cta.b64 _, [%0];" ::"r"(bar) : "memory"); }
__device__ __forceinline__ bool mbar_try(uint32_t bar, uint32_t parity) {
  uint32_t ok;
  asm volatile("{\n.reg .pred p;\nmbarrier.try_wait.parity.shared::cta.b64 p, [%1], %2;\nselp.u32 %0, 1, 0, p;\n}" : "=r"(ok) : "r"(bar), "r"(parity) : "memory");
  return ok;
}
__device__ __forceinline__ void mbar_wait(uint32_t bar, uint32_t parity) {
  if (mbar_try(bar, parity)) return;
  const uint32_t t0 = (uint32_t)clock();
  while (!mbar_try(bar, parity)) { if ((uint32_t)clock() - t0 > (1u << 30)) __trap(); }
}
__device__ __forceinline__ void poll_ge(const unsigned* p, unsigned target) {
  const uint32_t t0 = (uint32_t)clock();
  for (;;) {
    unsigned v;
    asm volatile("ld.acquire.gpu.global.u32 %0, [%1];" : "=r"(v) : "l"(p) : "memory");
    if ((int)(v - target) >= 0) return;
    if ((uint32_t)clock() - t0 > (1u << 30)) __trap();
  }
}
__device__ __forceinline__ void red_release(unsigned* p) { asm volatile("red.release.gpu.global.add.u32 [%0], 1;" ::"l"(p) : "memory"); }
__device__ __forceinline__ void tma2d(uint32_t dst, const CUtensorMap* m, uint32_t bar, int c0, int c1) {
  asm volatile("cp.async.bulk.tensor.2d.shared::cluster.global.mbarrier::complete_tx::bytes [%0], [%1, {%3, %4}], [%2];" ::"r"(dst), "l"(m), "r"(bar), "r"(c0), "r"(c1) : "memory");
}
__device__ __forceinline__ void tma3d(uint32_t dst, const CUtensorMap* m, uint32_t bar, int c0, int c1, int c2) {
  asm volatile("cp.async.bulk.tensor.3d.shared::cluster.global.mbarrier::complete_tx::bytes [%0], [%1, {%3, %4, %5}], [%2];" ::"r"(dst), "l"(m), "r"(bar), "r"(c0), "r"(c1), "r"(c2) : "memory");
}
__device__ __forceinline__ void tma4d(uint32_t dst, const CUtensorMap* m, uint32_t bar, int c0, int c1, int c2, int c3) {
  asm volatile("cp.async.bulk.tensor.4d.shared::cluster.global.mbarrier::complete_tx::bytes [%0], [%1, {%3, %4, %5, %6}], [%2];" ::"r"(dst), "l"(m), "r"(bar), "r"(c0), "r"(c1), "r"(c2), "r"(c3) : "memory");
}
__device__ __forceinline__ void l2_prefetch(const void* p, uint32_t bytes) { asm volatile("cp.async.bulk.prefetch.L2.global [%0], %1;" ::"l"(p), "r"(bytes) : "memory"); }
__device__ __forceinline__ void wg_fence() { asm volatile("wgmma.fence.sync.aligned;" ::: "memory"); }
__device__ __forceinline__ void wg_commit() { asm volatile("wgmma.commit_group.sync.aligned;" ::: "memory"); }
template <int N> __device__ __forceinline__ void wg_wait() { asm volatile("wgmma.wait_group.sync.aligned %0;" ::"n"(N) : "memory"); }
template <int O, int N, int NN> __device__ __forceinline__ void fence_regs(float (&d)[NN]) {
#pragma unroll
  for (int i = 0; i < N; i++) asm volatile("" : "+f"(d[O + i])::"memory");
}
__device__ __forceinline__ uint64_t mkdesc(uint32_t addr, uint32_t lbo, uint32_t sbo, uint32_t mode) {
  return (uint64_t)((addr & 0x3FFFF) >> 4) | ((uint64_t)(lbo >> 4) << 16) | ((uint64_t)(sbo >> 4) << 32) | ((uint64_t)mode << 62);
}
__device__ __forceinline__ uint32_t pack_bf16(float lo, float hi) {
  uint32_t r; asm("cvt.rn.bf16x2.f32 %0, %1, %2;" : "=r"(r) : "f"(hi), "f"(lo)); return r;
}
__device__ __forceinline__ uint32_t pack_pin(float lo, float hi) {
  uint32_t r; asm volatile("cvt.rn.bf16x2.f32 %0, %1, %2;" : "=r"(r) : "f"(hi), "f"(lo) : "memory"); return r;
}
__device__ __forceinline__ float bf_lo(uint32_t u) { return __uint_as_float(u << 16); }
__device__ __forceinline__ float bf_hi(uint32_t u) { return __uint_as_float(u & 0xffff0000u); }

template<int O,int TB,int ACC,int NN> __device__ __forceinline__ void mma_ss64(float (&d)[NN], uint64_t da, uint64_t db, int sd = 0){
  if constexpr (ACC == 1) asm volatile("wgmma.mma_async.sync.aligned.m64n64k16.f32.bf16.bf16 {%0,%1,%2,%3,%4,%5,%6,%7,%8,%9,%10,%11,%12,%13,%14,%15,%16,%17,%18,%19,%20,%21,%22,%23,%24,%25,%26,%27,%28,%29,%30,%31}, %32, %33, 1, 1, 1, 0, %34;"
   : "+f"(d[O+0]), "+f"(d[O+1]), "+f"(d[O+2]), "+f"(d[O+3]), "+f"(d[O+4]), "+f"(d[O+5]), "+f"(d[O+6]), "+f"(d[O+7]), "+f"(d[O+8]), "+f"(d[O+9]), "+f"(d[O+10]), "+f"(d[O+11]), "+f"(d[O+12]), "+f"(d[O+13]), "+f"(d[O+14]), "+f"(d[O+15]), "+f"(d[O+16]), "+f"(d[O+17]), "+f"(d[O+18]), "+f"(d[O+19]), "+f"(d[O+20]), "+f"(d[O+21]), "+f"(d[O+22]), "+f"(d[O+23]), "+f"(d[O+24]), "+f"(d[O+25]), "+f"(d[O+26]), "+f"(d[O+27]), "+f"(d[O+28]), "+f"(d[O+29]), "+f"(d[O+30]), "+f"(d[O+31])
   : "l"(da), "l"(db), "n"(TB));
  else if constexpr (ACC == 0) asm volatile("wgmma.mma_async.sync.aligned.m64n64k16.f32.bf16.bf16 {%0,%1,%2,%3,%4,%5,%6,%7,%8,%9,%10,%11,%12,%13,%14,%15,%16,%17,%18,%19,%20,%21,%22,%23,%24,%25,%26,%27,%28,%29,%30,%31}, %32, %33, 0, 1, 1, 0, %34;"
   : "=f"(d[O+0]), "=f"(d[O+1]), "=f"(d[O+2]), "=f"(d[O+3]), "=f"(d[O+4]), "=f"(d[O+5]), "=f"(d[O+6]), "=f"(d[O+7]), "=f"(d[O+8]), "=f"(d[O+9]), "=f"(d[O+10]), "=f"(d[O+11]), "=f"(d[O+12]), "=f"(d[O+13]), "=f"(d[O+14]), "=f"(d[O+15]), "=f"(d[O+16]), "=f"(d[O+17]), "=f"(d[O+18]), "=f"(d[O+19]), "=f"(d[O+20]), "=f"(d[O+21]), "=f"(d[O+22]), "=f"(d[O+23]), "=f"(d[O+24]), "=f"(d[O+25]), "=f"(d[O+26]), "=f"(d[O+27]), "=f"(d[O+28]), "=f"(d[O+29]), "=f"(d[O+30]), "=f"(d[O+31])
   : "l"(da), "l"(db), "n"(TB));
  else asm volatile("{\n.reg .pred p;\nsetp.ne.b32 p, %35, 0;\nwgmma.mma_async.sync.aligned.m64n64k16.f32.bf16.bf16 {%0,%1,%2,%3,%4,%5,%6,%7,%8,%9,%10,%11,%12,%13,%14,%15,%16,%17,%18,%19,%20,%21,%22,%23,%24,%25,%26,%27,%28,%29,%30,%31}, %32, %33, p, 1, 1, 0, %34;\n}"
   : "+f"(d[O+0]), "+f"(d[O+1]), "+f"(d[O+2]), "+f"(d[O+3]), "+f"(d[O+4]), "+f"(d[O+5]), "+f"(d[O+6]), "+f"(d[O+7]), "+f"(d[O+8]), "+f"(d[O+9]), "+f"(d[O+10]), "+f"(d[O+11]), "+f"(d[O+12]), "+f"(d[O+13]), "+f"(d[O+14]), "+f"(d[O+15]), "+f"(d[O+16]), "+f"(d[O+17]), "+f"(d[O+18]), "+f"(d[O+19]), "+f"(d[O+20]), "+f"(d[O+21]), "+f"(d[O+22]), "+f"(d[O+23]), "+f"(d[O+24]), "+f"(d[O+25]), "+f"(d[O+26]), "+f"(d[O+27]), "+f"(d[O+28]), "+f"(d[O+29]), "+f"(d[O+30]), "+f"(d[O+31])
   : "l"(da), "l"(db), "n"(TB), "r"(sd));
}
template<int O,int TB,int ACC,int NN> __device__ __forceinline__ void mma_rs64(float (&d)[NN], uint32_t a0, uint32_t a1, uint32_t a2, uint32_t a3, uint64_t db, int sd = 0){
  if constexpr (ACC == 1) asm volatile("wgmma.mma_async.sync.aligned.m64n64k16.f32.bf16.bf16 {%0,%1,%2,%3,%4,%5,%6,%7,%8,%9,%10,%11,%12,%13,%14,%15,%16,%17,%18,%19,%20,%21,%22,%23,%24,%25,%26,%27,%28,%29,%30,%31}, {%32,%33,%34,%35}, %36, 1, 1, 1, %37;"
   : "+f"(d[O+0]), "+f"(d[O+1]), "+f"(d[O+2]), "+f"(d[O+3]), "+f"(d[O+4]), "+f"(d[O+5]), "+f"(d[O+6]), "+f"(d[O+7]), "+f"(d[O+8]), "+f"(d[O+9]), "+f"(d[O+10]), "+f"(d[O+11]), "+f"(d[O+12]), "+f"(d[O+13]), "+f"(d[O+14]), "+f"(d[O+15]), "+f"(d[O+16]), "+f"(d[O+17]), "+f"(d[O+18]), "+f"(d[O+19]), "+f"(d[O+20]), "+f"(d[O+21]), "+f"(d[O+22]), "+f"(d[O+23]), "+f"(d[O+24]), "+f"(d[O+25]), "+f"(d[O+26]), "+f"(d[O+27]), "+f"(d[O+28]), "+f"(d[O+29]), "+f"(d[O+30]), "+f"(d[O+31])
   : "r"(a0), "r"(a1), "r"(a2), "r"(a3), "l"(db), "n"(TB));
  else if constexpr (ACC == 0) asm volatile("wgmma.mma_async.sync.aligned.m64n64k16.f32.bf16.bf16 {%0,%1,%2,%3,%4,%5,%6,%7,%8,%9,%10,%11,%12,%13,%14,%15,%16,%17,%18,%19,%20,%21,%22,%23,%24,%25,%26,%27,%28,%29,%30,%31}, {%32,%33,%34,%35}, %36, 0, 1, 1, %37;"
   : "=f"(d[O+0]), "=f"(d[O+1]), "=f"(d[O+2]), "=f"(d[O+3]), "=f"(d[O+4]), "=f"(d[O+5]), "=f"(d[O+6]), "=f"(d[O+7]), "=f"(d[O+8]), "=f"(d[O+9]), "=f"(d[O+10]), "=f"(d[O+11]), "=f"(d[O+12]), "=f"(d[O+13]), "=f"(d[O+14]), "=f"(d[O+15]), "=f"(d[O+16]), "=f"(d[O+17]), "=f"(d[O+18]), "=f"(d[O+19]), "=f"(d[O+20]), "=f"(d[O+21]), "=f"(d[O+22]), "=f"(d[O+23]), "=f"(d[O+24]), "=f"(d[O+25]), "=f"(d[O+26]), "=f"(d[O+27]), "=f"(d[O+28]), "=f"(d[O+29]), "=f"(d[O+30]), "=f"(d[O+31])
   : "r"(a0), "r"(a1), "r"(a2), "r"(a3), "l"(db), "n"(TB));
  else asm volatile("{\n.reg .pred p;\nsetp.ne.b32 p, %38, 0;\nwgmma.mma_async.sync.aligned.m64n64k16.f32.bf16.bf16 {%0,%1,%2,%3,%4,%5,%6,%7,%8,%9,%10,%11,%12,%13,%14,%15,%16,%17,%18,%19,%20,%21,%22,%23,%24,%25,%26,%27,%28,%29,%30,%31}, {%32,%33,%34,%35}, %36, p, 1, 1, %37;\n}"
   : "+f"(d[O+0]), "+f"(d[O+1]), "+f"(d[O+2]), "+f"(d[O+3]), "+f"(d[O+4]), "+f"(d[O+5]), "+f"(d[O+6]), "+f"(d[O+7]), "+f"(d[O+8]), "+f"(d[O+9]), "+f"(d[O+10]), "+f"(d[O+11]), "+f"(d[O+12]), "+f"(d[O+13]), "+f"(d[O+14]), "+f"(d[O+15]), "+f"(d[O+16]), "+f"(d[O+17]), "+f"(d[O+18]), "+f"(d[O+19]), "+f"(d[O+20]), "+f"(d[O+21]), "+f"(d[O+22]), "+f"(d[O+23]), "+f"(d[O+24]), "+f"(d[O+25]), "+f"(d[O+26]), "+f"(d[O+27]), "+f"(d[O+28]), "+f"(d[O+29]), "+f"(d[O+30]), "+f"(d[O+31])
   : "r"(a0), "r"(a1), "r"(a2), "r"(a3), "l"(db), "n"(TB), "r"(sd));
}
template<int O,int TB,int ACC,int NN> __device__ __forceinline__ void mma_ss128(float (&d)[NN], uint64_t da, uint64_t db, int sd = 0){
  if constexpr (ACC == 1) asm volatile("wgmma.mma_async.sync.aligned.m64n128k16.f32.bf16.bf16 {%0,%1,%2,%3,%4,%5,%6,%7,%8,%9,%10,%11,%12,%13,%14,%15,%16,%17,%18,%19,%20,%21,%22,%23,%24,%25,%26,%27,%28,%29,%30,%31,%32,%33,%34,%35,%36,%37,%38,%39,%40,%41,%42,%43,%44,%45,%46,%47,%48,%49,%50,%51,%52,%53,%54,%55,%56,%57,%58,%59,%60,%61,%62,%63}, %64, %65, 1, 1, 1, 0, %66;"
   : "+f"(d[O+0]), "+f"(d[O+1]), "+f"(d[O+2]), "+f"(d[O+3]), "+f"(d[O+4]), "+f"(d[O+5]), "+f"(d[O+6]), "+f"(d[O+7]), "+f"(d[O+8]), "+f"(d[O+9]), "+f"(d[O+10]), "+f"(d[O+11]), "+f"(d[O+12]), "+f"(d[O+13]), "+f"(d[O+14]), "+f"(d[O+15]), "+f"(d[O+16]), "+f"(d[O+17]), "+f"(d[O+18]), "+f"(d[O+19]), "+f"(d[O+20]), "+f"(d[O+21]), "+f"(d[O+22]), "+f"(d[O+23]), "+f"(d[O+24]), "+f"(d[O+25]), "+f"(d[O+26]), "+f"(d[O+27]), "+f"(d[O+28]), "+f"(d[O+29]), "+f"(d[O+30]), "+f"(d[O+31]), "+f"(d[O+32]), "+f"(d[O+33]), "+f"(d[O+34]), "+f"(d[O+35]), "+f"(d[O+36]), "+f"(d[O+37]), "+f"(d[O+38]), "+f"(d[O+39]), "+f"(d[O+40]), "+f"(d[O+41]), "+f"(d[O+42]), "+f"(d[O+43]), "+f"(d[O+44]), "+f"(d[O+45]), "+f"(d[O+46]), "+f"(d[O+47]), "+f"(d[O+48]), "+f"(d[O+49]), "+f"(d[O+50]), "+f"(d[O+51]), "+f"(d[O+52]), "+f"(d[O+53]), "+f"(d[O+54]), "+f"(d[O+55]), "+f"(d[O+56]), "+f"(d[O+57]), "+f"(d[O+58]), "+f"(d[O+59]), "+f"(d[O+60]), "+f"(d[O+61]), "+f"(d[O+62]), "+f"(d[O+63])
   : "l"(da), "l"(db), "n"(TB));
  else if constexpr (ACC == 0) asm volatile("wgmma.mma_async.sync.aligned.m64n128k16.f32.bf16.bf16 {%0,%1,%2,%3,%4,%5,%6,%7,%8,%9,%10,%11,%12,%13,%14,%15,%16,%17,%18,%19,%20,%21,%22,%23,%24,%25,%26,%27,%28,%29,%30,%31,%32,%33,%34,%35,%36,%37,%38,%39,%40,%41,%42,%43,%44,%45,%46,%47,%48,%49,%50,%51,%52,%53,%54,%55,%56,%57,%58,%59,%60,%61,%62,%63}, %64, %65, 0, 1, 1, 0, %66;"
   : "=f"(d[O+0]), "=f"(d[O+1]), "=f"(d[O+2]), "=f"(d[O+3]), "=f"(d[O+4]), "=f"(d[O+5]), "=f"(d[O+6]), "=f"(d[O+7]), "=f"(d[O+8]), "=f"(d[O+9]), "=f"(d[O+10]), "=f"(d[O+11]), "=f"(d[O+12]), "=f"(d[O+13]), "=f"(d[O+14]), "=f"(d[O+15]), "=f"(d[O+16]), "=f"(d[O+17]), "=f"(d[O+18]), "=f"(d[O+19]), "=f"(d[O+20]), "=f"(d[O+21]), "=f"(d[O+22]), "=f"(d[O+23]), "=f"(d[O+24]), "=f"(d[O+25]), "=f"(d[O+26]), "=f"(d[O+27]), "=f"(d[O+28]), "=f"(d[O+29]), "=f"(d[O+30]), "=f"(d[O+31]), "=f"(d[O+32]), "=f"(d[O+33]), "=f"(d[O+34]), "=f"(d[O+35]), "=f"(d[O+36]), "=f"(d[O+37]), "=f"(d[O+38]), "=f"(d[O+39]), "=f"(d[O+40]), "=f"(d[O+41]), "=f"(d[O+42]), "=f"(d[O+43]), "=f"(d[O+44]), "=f"(d[O+45]), "=f"(d[O+46]), "=f"(d[O+47]), "=f"(d[O+48]), "=f"(d[O+49]), "=f"(d[O+50]), "=f"(d[O+51]), "=f"(d[O+52]), "=f"(d[O+53]), "=f"(d[O+54]), "=f"(d[O+55]), "=f"(d[O+56]), "=f"(d[O+57]), "=f"(d[O+58]), "=f"(d[O+59]), "=f"(d[O+60]), "=f"(d[O+61]), "=f"(d[O+62]), "=f"(d[O+63])
   : "l"(da), "l"(db), "n"(TB));
  else asm volatile("{\n.reg .pred p;\nsetp.ne.b32 p, %67, 0;\nwgmma.mma_async.sync.aligned.m64n128k16.f32.bf16.bf16 {%0,%1,%2,%3,%4,%5,%6,%7,%8,%9,%10,%11,%12,%13,%14,%15,%16,%17,%18,%19,%20,%21,%22,%23,%24,%25,%26,%27,%28,%29,%30,%31,%32,%33,%34,%35,%36,%37,%38,%39,%40,%41,%42,%43,%44,%45,%46,%47,%48,%49,%50,%51,%52,%53,%54,%55,%56,%57,%58,%59,%60,%61,%62,%63}, %64, %65, p, 1, 1, 0, %66;\n}"
   : "+f"(d[O+0]), "+f"(d[O+1]), "+f"(d[O+2]), "+f"(d[O+3]), "+f"(d[O+4]), "+f"(d[O+5]), "+f"(d[O+6]), "+f"(d[O+7]), "+f"(d[O+8]), "+f"(d[O+9]), "+f"(d[O+10]), "+f"(d[O+11]), "+f"(d[O+12]), "+f"(d[O+13]), "+f"(d[O+14]), "+f"(d[O+15]), "+f"(d[O+16]), "+f"(d[O+17]), "+f"(d[O+18]), "+f"(d[O+19]), "+f"(d[O+20]), "+f"(d[O+21]), "+f"(d[O+22]), "+f"(d[O+23]), "+f"(d[O+24]), "+f"(d[O+25]), "+f"(d[O+26]), "+f"(d[O+27]), "+f"(d[O+28]), "+f"(d[O+29]), "+f"(d[O+30]), "+f"(d[O+31]), "+f"(d[O+32]), "+f"(d[O+33]), "+f"(d[O+34]), "+f"(d[O+35]), "+f"(d[O+36]), "+f"(d[O+37]), "+f"(d[O+38]), "+f"(d[O+39]), "+f"(d[O+40]), "+f"(d[O+41]), "+f"(d[O+42]), "+f"(d[O+43]), "+f"(d[O+44]), "+f"(d[O+45]), "+f"(d[O+46]), "+f"(d[O+47]), "+f"(d[O+48]), "+f"(d[O+49]), "+f"(d[O+50]), "+f"(d[O+51]), "+f"(d[O+52]), "+f"(d[O+53]), "+f"(d[O+54]), "+f"(d[O+55]), "+f"(d[O+56]), "+f"(d[O+57]), "+f"(d[O+58]), "+f"(d[O+59]), "+f"(d[O+60]), "+f"(d[O+61]), "+f"(d[O+62]), "+f"(d[O+63])
   : "l"(da), "l"(db), "n"(TB), "r"(sd));
}
template<int O,int TB,int ACC,int NN> __device__ __forceinline__ void mma_rs128(float (&d)[NN], uint32_t a0, uint32_t a1, uint32_t a2, uint32_t a3, uint64_t db, int sd = 0){
  if constexpr (ACC == 1) asm volatile("wgmma.mma_async.sync.aligned.m64n128k16.f32.bf16.bf16 {%0,%1,%2,%3,%4,%5,%6,%7,%8,%9,%10,%11,%12,%13,%14,%15,%16,%17,%18,%19,%20,%21,%22,%23,%24,%25,%26,%27,%28,%29,%30,%31,%32,%33,%34,%35,%36,%37,%38,%39,%40,%41,%42,%43,%44,%45,%46,%47,%48,%49,%50,%51,%52,%53,%54,%55,%56,%57,%58,%59,%60,%61,%62,%63}, {%64,%65,%66,%67}, %68, 1, 1, 1, %69;"
   : "+f"(d[O+0]), "+f"(d[O+1]), "+f"(d[O+2]), "+f"(d[O+3]), "+f"(d[O+4]), "+f"(d[O+5]), "+f"(d[O+6]), "+f"(d[O+7]), "+f"(d[O+8]), "+f"(d[O+9]), "+f"(d[O+10]), "+f"(d[O+11]), "+f"(d[O+12]), "+f"(d[O+13]), "+f"(d[O+14]), "+f"(d[O+15]), "+f"(d[O+16]), "+f"(d[O+17]), "+f"(d[O+18]), "+f"(d[O+19]), "+f"(d[O+20]), "+f"(d[O+21]), "+f"(d[O+22]), "+f"(d[O+23]), "+f"(d[O+24]), "+f"(d[O+25]), "+f"(d[O+26]), "+f"(d[O+27]), "+f"(d[O+28]), "+f"(d[O+29]), "+f"(d[O+30]), "+f"(d[O+31]), "+f"(d[O+32]), "+f"(d[O+33]), "+f"(d[O+34]), "+f"(d[O+35]), "+f"(d[O+36]), "+f"(d[O+37]), "+f"(d[O+38]), "+f"(d[O+39]), "+f"(d[O+40]), "+f"(d[O+41]), "+f"(d[O+42]), "+f"(d[O+43]), "+f"(d[O+44]), "+f"(d[O+45]), "+f"(d[O+46]), "+f"(d[O+47]), "+f"(d[O+48]), "+f"(d[O+49]), "+f"(d[O+50]), "+f"(d[O+51]), "+f"(d[O+52]), "+f"(d[O+53]), "+f"(d[O+54]), "+f"(d[O+55]), "+f"(d[O+56]), "+f"(d[O+57]), "+f"(d[O+58]), "+f"(d[O+59]), "+f"(d[O+60]), "+f"(d[O+61]), "+f"(d[O+62]), "+f"(d[O+63])
   : "r"(a0), "r"(a1), "r"(a2), "r"(a3), "l"(db), "n"(TB));
  else if constexpr (ACC == 0) asm volatile("wgmma.mma_async.sync.aligned.m64n128k16.f32.bf16.bf16 {%0,%1,%2,%3,%4,%5,%6,%7,%8,%9,%10,%11,%12,%13,%14,%15,%16,%17,%18,%19,%20,%21,%22,%23,%24,%25,%26,%27,%28,%29,%30,%31,%32,%33,%34,%35,%36,%37,%38,%39,%40,%41,%42,%43,%44,%45,%46,%47,%48,%49,%50,%51,%52,%53,%54,%55,%56,%57,%58,%59,%60,%61,%62,%63}, {%64,%65,%66,%67}, %68, 0, 1, 1, %69;"
   : "=f"(d[O+0]), "=f"(d[O+1]), "=f"(d[O+2]), "=f"(d[O+3]), "=f"(d[O+4]), "=f"(d[O+5]), "=f"(d[O+6]), "=f"(d[O+7]), "=f"(d[O+8]), "=f"(d[O+9]), "=f"(d[O+10]), "=f"(d[O+11]), "=f"(d[O+12]), "=f"(d[O+13]), "=f"(d[O+14]), "=f"(d[O+15]), "=f"(d[O+16]), "=f"(d[O+17]), "=f"(d[O+18]), "=f"(d[O+19]), "=f"(d[O+20]), "=f"(d[O+21]), "=f"(d[O+22]), "=f"(d[O+23]), "=f"(d[O+24]), "=f"(d[O+25]), "=f"(d[O+26]), "=f"(d[O+27]), "=f"(d[O+28]), "=f"(d[O+29]), "=f"(d[O+30]), "=f"(d[O+31]), "=f"(d[O+32]), "=f"(d[O+33]), "=f"(d[O+34]), "=f"(d[O+35]), "=f"(d[O+36]), "=f"(d[O+37]), "=f"(d[O+38]), "=f"(d[O+39]), "=f"(d[O+40]), "=f"(d[O+41]), "=f"(d[O+42]), "=f"(d[O+43]), "=f"(d[O+44]), "=f"(d[O+45]), "=f"(d[O+46]), "=f"(d[O+47]), "=f"(d[O+48]), "=f"(d[O+49]), "=f"(d[O+50]), "=f"(d[O+51]), "=f"(d[O+52]), "=f"(d[O+53]), "=f"(d[O+54]), "=f"(d[O+55]), "=f"(d[O+56]), "=f"(d[O+57]), "=f"(d[O+58]), "=f"(d[O+59]), "=f"(d[O+60]), "=f"(d[O+61]), "=f"(d[O+62]), "=f"(d[O+63])
   : "r"(a0), "r"(a1), "r"(a2), "r"(a3), "l"(db), "n"(TB));
  else asm volatile("{\n.reg .pred p;\nsetp.ne.b32 p, %70, 0;\nwgmma.mma_async.sync.aligned.m64n128k16.f32.bf16.bf16 {%0,%1,%2,%3,%4,%5,%6,%7,%8,%9,%10,%11,%12,%13,%14,%15,%16,%17,%18,%19,%20,%21,%22,%23,%24,%25,%26,%27,%28,%29,%30,%31,%32,%33,%34,%35,%36,%37,%38,%39,%40,%41,%42,%43,%44,%45,%46,%47,%48,%49,%50,%51,%52,%53,%54,%55,%56,%57,%58,%59,%60,%61,%62,%63}, {%64,%65,%66,%67}, %68, p, 1, 1, %69;\n}"
   : "+f"(d[O+0]), "+f"(d[O+1]), "+f"(d[O+2]), "+f"(d[O+3]), "+f"(d[O+4]), "+f"(d[O+5]), "+f"(d[O+6]), "+f"(d[O+7]), "+f"(d[O+8]), "+f"(d[O+9]), "+f"(d[O+10]), "+f"(d[O+11]), "+f"(d[O+12]), "+f"(d[O+13]), "+f"(d[O+14]), "+f"(d[O+15]), "+f"(d[O+16]), "+f"(d[O+17]), "+f"(d[O+18]), "+f"(d[O+19]), "+f"(d[O+20]), "+f"(d[O+21]), "+f"(d[O+22]), "+f"(d[O+23]), "+f"(d[O+24]), "+f"(d[O+25]), "+f"(d[O+26]), "+f"(d[O+27]), "+f"(d[O+28]), "+f"(d[O+29]), "+f"(d[O+30]), "+f"(d[O+31]), "+f"(d[O+32]), "+f"(d[O+33]), "+f"(d[O+34]), "+f"(d[O+35]), "+f"(d[O+36]), "+f"(d[O+37]), "+f"(d[O+38]), "+f"(d[O+39]), "+f"(d[O+40]), "+f"(d[O+41]), "+f"(d[O+42]), "+f"(d[O+43]), "+f"(d[O+44]), "+f"(d[O+45]), "+f"(d[O+46]), "+f"(d[O+47]), "+f"(d[O+48]), "+f"(d[O+49]), "+f"(d[O+50]), "+f"(d[O+51]), "+f"(d[O+52]), "+f"(d[O+53]), "+f"(d[O+54]), "+f"(d[O+55]), "+f"(d[O+56]), "+f"(d[O+57]), "+f"(d[O+58]), "+f"(d[O+59]), "+f"(d[O+60]), "+f"(d[O+61]), "+f"(d[O+62]), "+f"(d[O+63])
   : "r"(a0), "r"(a1), "r"(a2), "r"(a3), "l"(db), "n"(TB), "r"(sd));
}

__host__ __device__ constexpr int brev(int a, int bits) { int r = 0; for (int i = 0; i < bits; i++) r |= ((a >> i) & 1) << (bits - 1 - i); return r; }
__host__ __device__ constexpr int ilog2(int n) { return n <= 1 ? 0 : 1 + ilog2(n / 2); }
template <int SG, int A> __device__ __forceinline__ void bfly(float2& a, float2& b) {
  if constexpr (A == 0) {
    float tr = a.x - b.x, ti = a.y - b.y; a.x += b.x; a.y += b.y; b.x = tr; b.y = ti;
  } else if constexpr (A == 8) {
    float pr = SG > 0 ? -b.y : b.y, pi = SG > 0 ? b.x : -b.x;
    b.x = a.x - pr; b.y = a.y - pi; a.x += pr; a.y += pi;
  } else {
    constexpr float wr = tbl::W32<A>::c, wi = SG * tbl::W32<A>::s;
    float tr = fmaf(wr, b.x, a.x), ti = fmaf(wr, b.y, a.y);
    tr = fmaf(-wi, b.y, tr); ti = fmaf(wi, b.x, ti);
    b.x = fmaf(2.f, a.x, -tr); b.y = fmaf(2.f, a.y, -ti); a.x = tr; a.y = ti;
  }
}
template <int SG, int N, int O, int ST, int A> __device__ __forceinline__ void dft_comb(float2 (&x)[32]) {
  if constexpr (A < N / 2) {
    constexpr int p = O + 2 * ST * brev(A, ilog2(N / 2));
    bfly<SG, A * (32 / N)>(x[p], x[p + ST]);
    dft_comb<SG, N, O, ST, A + 1>(x);
  }
}
template <int SG, int N, int O, int ST> __device__ __forceinline__ void dft(float2 (&x)[32]) {
  if constexpr (N > 1) {
    dft<SG, N / 2, O, 2 * ST>(x);
    dft<SG, N / 2, O + ST, 2 * ST>(x);
    dft_comb<SG, N, O, ST, 0>(x);
  }
}

#define MAPMODE 1
struct I0 { static constexpr int value = 0; };
struct I1 { static constexpr int value = 1; };
struct I2 { static constexpr int value = 2; };
struct I32 { static constexpr int value = 32; };
struct Maps { CUtensorMap x, ft, fg, e, g64, u64, g32, u32, d96, d32, t; };

constexpr int SLOT = 16384;
constexpr int NSLOT = 13;
constexpr int OFF_W = NSLOT * SLOT;
constexpr int OFF_GW = OFF_W + SLOT;
constexpr int OFF_G = OFF_GW + 1024;
constexpr int OFF_BAR = OFF_G + 512;
constexpr int SMEM_BYTES = OFF_BAR + 512;
constexpr int B_FULL = 0, B_EMPTY = 13, B_G = 26, B_X1 = 27, B_XR = 28, B_T = 29, B_R = 30, B_P = 31;

__device__ __forceinline__ int ringB(int m) {
  return (int)((0xB7A69584C3210ULL >> (4 * m)) & 15);
}

__global__ void __launch_bounds__(512, 1)
fused_kernel(const __grid_constant__ Maps maps, const __nv_bfloat16* __restrict__ w_r, const __nv_bfloat16* __restrict__ w_i,
             const __nv_bfloat16* __restrict__ gate_w, const __nv_bfloat16* __restrict__ Wg, const __nv_bfloat16* __restrict__ Wu,
             const __nv_bfloat16* __restrict__ Wd, __nv_bfloat16* __restrict__ out) {
  extern __shared__ __align__(1024) uint8_t smem[];
  const uint32_t sb = smem_u32(smem);
  const uint32_t bars = sb + OFF_BAR;
  const int tid = threadIdx.x, warp = tid >> 5, lane = tid & 31;
  const bool helper = blockIdx.x == 128;
  const int idx = (blockIdx.x + 120) & 127;
  const int rb = ((idx >> 5) << 2) | ((idx >> 2) & 3), j = (((idx >> 4) & 1) << 2) | (idx & 3);
  const int fm = 448 * (j >> 1);
  const int f_full = fm + ((j & 1) ? 256 : 0);
  const int f_half = fm + ((j & 1) ? 224 : 192);

  if (tid == 0) {
    PROF_EV(0);
    for (int i = 0; i < NSLOT; i++) { mbar_init(bars + 8 * (B_FULL + i), 1); mbar_init(bars + 8 * (B_EMPTY + i), 2); }
    mbar_init(bars + 8 * B_G, 4); mbar_init(bars + 8 * B_X1, 8); mbar_init(bars + 8 * B_XR, 1);
    mbar_init(bars + 8 * B_T, 1); mbar_init(bars + 8 * B_R, 1);
    for (int i = 0; i < 7; i++) mbar_init(bars + 8 * (B_P + i), 8);
    asm volatile("fence.mbarrier_init.release.cluster;" ::: "memory");
  }
  __syncthreads();

  if (warp >= 12) {
    asm volatile("setmaxnreg.dec.sync.aligned.u32 32;");
    if (warp == 12 && lane == 0 && !helper) {
      uint32_t eph = 0xFFFFFFFFu;
      auto acquire = [&](int s, uint32_t bytes) {
        mbar_wait(bars + 8 * (B_EMPTY + s), (eph >> s) & 1); eph ^= 1u << s;
        mbar_expect_tx(bars + 8 * (B_FULL + s), bytes);
      };
      auto loadE = [&](int s, int w) { acquire(s, SLOT); tma4d(sb + s * SLOT, &maps.e, bars + 8 * (B_FULL + s), 0, 0, 0, 2 * rb + w); };
      auto loadB = [&](int m) {
        const int s = ringB(m >= 13 ? m - 13 : m);
        if (m < 2) { loadE(s, m); return; }
        const int t = (m - 2) / 3, p = (m - 2) - 3 * t;
        const int col = 64 * ((j + 1 + t) & 7);
        const uint32_t fb = bars + 8 * (B_FULL + s);
        acquire(s, 12288);
        if (p < 2) tma2d(sb + s * SLOT, &maps.d96, fb, col, f_full + 96 * p);
        else { tma4d(sb + s * SLOT, &maps.fg, fb, col, 0, 0, 4 * j); tma2d(sb + s * SLOT + 8192, &maps.d32, fb, col, f_half); }
      };
      int rs = 8;
      for (int n = 0; n < 34; n++) {
        const uint32_t fb = bars + 8 * (B_FULL + rs), dst = sb + rs * SLOT;
        if (n < 5)
          for (int q = n; q < (n == 4 ? 8 : n + 1); q++) { acquire(q, SLOT); tma3d(sb + q * SLOT, &maps.x, bars + 8 * (B_FULL + q), 64 * q, 0, 2 * rb); }
        if (n < 8) {
          acquire(rs, SLOT);
          tma2d(dst, &maps.ft, fb, 64 * n, 64 * j);
          tma2d(dst + 8192, &maps.g32, fb, f_half, 64 * n);
          tma2d(dst + 12288, &maps.u32, fb, f_half, 64 * n);
        } else if (n == 9 || n == 10) {
          loadE(rs, n - 9);
        } else {
          const int q = n == 8 ? 0 : n - 10;
          acquire(rs, SLOT);
          tma2d(dst, &maps.g64, fb, f_full + 64 * (q >> 3), 64 * (q & 7));
          tma2d(dst + 8192, &maps.u64, fb, f_full + 64 * (q >> 3), 64 * (q & 7));
          if (n >= 31) loadB(n - 31);
        }
        if (++rs == 13) rs = 8;
      }
      for (int m = 3; m < 26; m++) loadB(m);
    } else if (warp == 13 && lane == 0 && !helper) {
      mbar_wait(bars + 8 * B_X1, 0);
      red_release(&g_cntX[32 * j]);
      PROF_EV(20);
      for (int t = 0; t < 7; t++) {
        mbar_wait(bars + 8 * (B_P + t), 0);
        red_release(&g_cntP[32 * (rb * 8 + ((j + 1 + t) & 7))]);
      }
      PROF_EV(21);
    } else if (warp == 14 && lane == 0) {
      const unsigned ep = atomicAdd(&g_ticket, 1u) / 129u + 1u;
      const int jj = helper ? 0 : j;
      poll_ge(&g_cntX[32 * jj], ep * 16u);
      mbar_arrive(bars + 8 * B_XR);
      PROF_EV(22);
      if (!helper) {
        poll_ge(&g_cntT[32 * j], ep * (j == 0 ? 17u : 16u));
        asm volatile("fence.proxy.async;" ::: "memory");
        mbar_expect_tx(bars + 8 * B_T, SLOT);
        tma3d(sb + OFF_W, &maps.t, bars + 8 * B_T, 64 * j, 0, 2 * rb);
        PROF_EV(23);
        poll_ge(&g_cntP[32 * (rb * 8 + j)], ep * 7u);
        mbar_arrive(bars + 8 * B_R);
        PROF_EV(24);
      }
    } else if (warp == 15 && lane == 0 && !helper) {
      const int b = blockIdx.x;
      l2_prefetch((const char*)Wg + b * 14336, 14336);
      l2_prefetch((const char*)Wu + b * 14336, 14336);
      l2_prefetch((const char*)g_ET.v + b * 4096, 4096);
      l2_prefetch((const char*)w_r + b * 8224, 8224);
      l2_prefetch((const char*)w_i + b * 8224, 8224);
      l2_prefetch((const char*)Wd + b * 14336, 14336);
    }
  } else if (warp >= 8) {
    asm volatile("setmaxnreg.dec.sync.aligned.u32 80;");
    const int t = tid - 256, w = warp - 8;
    const float scale = 2.0f / (2048.0f * 512.0f);
    if (!helper) {
      if (t < 64) *(uint4*)(smem + OFF_GW + t * 16) = *(const uint4*)((const char*)gate_w + t * 16);
      asm volatile("bar.sync 1, 128;" ::: "memory");
      float z0[4] = {0, 0, 0, 0}, z1[4] = {0, 0, 0, 0};
      const int r0 = 32 * w + (lane & 15), ch = lane >> 4;
#pragma unroll 1
      for (int kb = 0; kb < 8; kb++) {
        mbar_wait(bars + 8 * (B_FULL + kb), 0);
#pragma unroll
        for (int h = 0; h < 2; h++) {
          uint32_t b[4];
          asm volatile("ldmatrix.sync.aligned.m8n8.x4.shared.b16 {%0,%1,%2,%3}, [%4];" : "=r"(b[0]), "=r"(b[1]), "=r"(b[2]), "=r"(b[3]) : "r"(sb + OFF_GW + kb * 128 + h * 64 + (lane >> 3) * 16));
#pragma unroll
          for (int u = 0; u < 2; u++) {
            const int c = 4 * h + 2 * u + ch;
            uint32_t a[4];
            asm volatile("ldmatrix.sync.aligned.m8n8.x4.shared.b16 {%0,%1,%2,%3}, [%4];" : "=r"(a[0]), "=r"(a[1]), "=r"(a[2]), "=r"(a[3]) : "r"(sb + kb * SLOT + r0 * 128 + ((c ^ (r0 & 7)) << 4)));
            asm volatile("mma.sync.aligned.m16n8k16.row.col.f32.bf16.bf16.f32 {%0,%1,%2,%3}, {%4,%5,%6,%7}, {%8,%9}, {%0,%1,%2,%3};"
                         : "+f"(z0[0]), "+f"(z0[1]), "+f"(z0[2]), "+f"(z0[3]) : "r"(a[0]), "r"(a[1]), "r"(a[2]), "r"(a[3]), "r"(b[2 * u]), "r"(b[2 * u + 1]));
            asm volatile("ldmatrix.sync.aligned.m8n8.x4.shared.b16 {%0,%1,%2,%3}, [%4];" : "=r"(a[0]), "=r"(a[1]), "=r"(a[2]), "=r"(a[3]) : "r"(sb + kb * SLOT + (r0 + 16) * 128 + ((c ^ (r0 & 7)) << 4)));
            asm volatile("mma.sync.aligned.m16n8k16.row.col.f32.bf16.bf16.f32 {%0,%1,%2,%3}, {%4,%5,%6,%7}, {%8,%9}, {%0,%1,%2,%3};"
                         : "+f"(z1[0]), "+f"(z1[1]), "+f"(z1[2]), "+f"(z1[3]) : "r"(a[0]), "r"(a[1]), "r"(a[2]), "r"(a[3]), "r"(b[2 * u]), "r"(b[2 * u + 1]));
          }
        }
      }
      {
        const int q = lane & 3;
        const float z = q == 0 ? z0[0] : q == 1 ? z0[2] : q == 2 ? z1[0] : z1[2];
        ((float*)(smem + OFF_G))[32 * w + 8 * q + (lane >> 2)] = 1.0f / (1.0f + __expf(-z));
        __syncwarp();
        if (lane == 0) mbar_arrive(bars + 8 * B_G);
      }
      if (t == 0) PROF_EV(10);
      const int kg = 2 * j + (rb >> 3), n = rb & 7;
      const int k = 16 * kg + (t & 15), j1 = 8 * n + (t >> 4);
      {
        const unsigned short* pr = (const unsigned short*)w_r + j1 * 257 + k;
        const unsigned short* pi = (const unsigned short*)w_i + j1 * 257 + k;
        uint32_t wv[32];
#pragma unroll
        for (int a = 0; a < 32; a++) wv[a] = (uint32_t)__ldg(pr + a * 64 * 257) | ((uint32_t)__ldg(pi + a * 64 * 257) << 16);
#pragma unroll
        for (int a = 0; a < 8; a++) *(uint4*)(smem + OFF_W + (a * 128 + t) * 16) = make_uint4(wv[4 * a], wv[4 * a + 1], wv[4 * a + 2], wv[4 * a + 3]);
      }
      if (t == 0) PROF_EV(11);
      mbar_wait(bars + 8 * B_XR, 0);
      float2 v[32];
      const float2* src = g_X1p + (size_t)(kg * 8 + n) * 4096 + t;
#pragma unroll
      for (int a = 0; a < 32; a++) v[a] = __ldcg(src + a * 128);
      dft<-1, 32, 0, 1>(v);
      if (t == 0) PROF_EV(12);
      float2 y[32];
#pragma unroll
      for (int a4 = 0; a4 < 8; a4++) {
        const uint4 ww = *(const uint4*)(smem + OFF_W + (a4 * 128 + t) * 16);
        const uint32_t wq[4] = {ww.x, ww.y, ww.z, ww.w};
#pragma unroll
        for (int e = 0; e < 4; e++) {
          const float2 z = v[brev(4 * a4 + e, 5)];
          const float wr = bf_lo(wq[e]), wi = bf_hi(wq[e]);
          y[4 * a4 + e] = make_float2(fmaf(z.x, wr, -z.y * wi), fmaf(z.x, wi, z.y * wr));
        }
      }
      dft<1, 32, 0, 1>(y);
      if (k != 0) {
        uint32_t* dst = g_Tp + j1 * 256 + k;
#pragma unroll
        for (int a = 0; a < 32; a++) dst[a * 64 * 256] = pack_bf16(y[brev(a, 5)].x * scale, y[brev(a, 5)].y * scale);
      }
      asm volatile("fence.proxy.async;" ::: "memory");
      asm volatile("bar.sync 1, 128;" ::: "memory");
      if (t == 0) { red_release(&g_cntT[32 * j]); PROF_EV(13); }
    } else {
      const int c = t >> 6, j1 = t & 63, k = c * 256;
      float2* ex = (float2*)smem;
      float2* wf = (float2*)(smem + 65536);
#pragma unroll 4
      for (int a = 0; a < 32; a++) {
        const int jj = j1 + 64 * a, jm = (2048 - jj) & 2047;
        const float wr = 0.5f * (__bfloat162float(w_r[jj * 257 + k]) + __bfloat162float(w_r[jm * 257 + k]));
        const float wi = 0.5f * (__bfloat162float(w_i[jj * 257 + k]) - __bfloat162float(w_i[jm * 257 + k]));
        wf[a * 128 + t] = c ? make_float2(-wi, wr) : make_float2(wr, wi);
      }
      mbar_wait(bars + 8 * B_XR, 0);
      float2 v[32];
#pragma unroll
      for (int a = 0; a < 32; a++) v[a] = __ldcg(g_X1s + (c * 32 + a) * 64 + j1);
      dft<-1, 32, 0, 1>(v);
      float2 y[32];
#pragma unroll
      for (int a = 0; a < 32; a++) {
        const float2 z = v[brev(a, 5)], wv = wf[a * 128 + t];
        y[a] = make_float2(fmaf(z.x, wv.x, -z.y * wv.y), fmaf(z.x, wv.y, z.y * wv.x));
      }
      dft<1, 32, 0, 1>(y);
      if (c) {
#pragma unroll
        for (int a = 0; a < 32; a++) ex[a * 64 + j1] = y[brev(a, 5)];
      }
      asm volatile("bar.sync 1, 128;" ::: "memory");
      if (!c) {
#pragma unroll
        for (int a = 0; a < 32; a++) {
          const float2 o = ex[a * 64 + j1];
          g_Tp[(a * 64 + j1) * 256] = pack_bf16((y[brev(a, 5)].x + o.x) * (0.5f * scale), (y[brev(a, 5)].y + o.y) * (0.5f * scale));
        }
      }
      asm volatile("fence.proxy.async;" ::: "memory");
      asm volatile("bar.sync 1, 128;" ::: "memory");
      if (t == 0) red_release(&g_cntT[0]);
    }
  } else {
    asm volatile("setmaxnreg.inc.sync.aligned.u32 200;");
    if (!helper) {
      const int wg = warp >> 2, w = warp & 3, g = lane >> 2, q = lane & 3;
      const bool elect = (tid & 127) == 0;
      uint32_t fph = 0;
      auto waitfull = [&](int s) { mbar_wait(bars + 8 * (B_FULL + s), (fph >> s) & 1); fph ^= 1u << s; };
      auto release = [&](int s) { if (elect) mbar_arrive(bars + 8 * (B_EMPTY + s)); };
      float c1[64], cA[64], c2[64], ci[64], ct[64];
      const int zero = blockIdx.x >> 16;
      uint32_t h[56], yf[16];
      const uint64_t dK = mkdesc(sb, 16, 1024, 1);
      const uint64_t dN = mkdesc(sb, 8192, 1024, 1);
      const uint64_t dM = mkdesc(sb, 4096, 512, 2);
      const uint32_t xo = wg * 512;
      int rs = 8, prev = 8;

      auto c1_step = [&](auto first, int kb) {
        waitfull(kb); waitfull(rs);
        wg_fence();
        const uint64_t dx = dK + (kb * 1024 + xo), df = dK + rs * 1024, dm = dM + (rs * 1024 + 512);
        mma_ss64<0, 0, decltype(first)::value>(c1, df, dx);
        mma_ss64<32, 1, decltype(first)::value>(c1, dx, dm);
#pragma unroll
        for (int k = 1; k < 4; k++) {
          mma_ss64<0, 0, 1>(c1, df + k * 2, dx + k * 2);
          mma_ss64<32, 1, 1>(c1, dx + k * 2, dm + k * 64);
        }
        wg_commit();
      };
      c1_step(I0(), 0);
      if (tid == 0) PROF_EV(1);
      rs = 9;
#pragma unroll 1
      for (int kb = 1; kb < 8; kb++) {
        c1_step(I1(), kb);
        wg_wait<1>();
        release(prev);
        prev = rs; if (++rs == 13) rs = 8;
      }
      auto ffn_step = [&](auto first, float (&acc)[64], int kb) {
        waitfull(rs);
        wg_fence();
        const uint64_t dx = dK + (kb * 1024 + xo), db = dN + rs * 1024;
        mma_ss128<0, 1, decltype(first)::value>(acc, dx, db, zero);
#pragma unroll
        for (int k = 1; k < 4; k++) mma_ss128<0, 1, 1>(acc, dx + k * 2, db + k * 128);
        wg_commit();
        wg_wait<1>();
      };
      ffn_step(I0(), c2, 0);
      release(prev); prev = rs; if (++rs == 13) rs = 8;
      fence_regs<0, 64>(c1);
      if (tid == 0) PROF_EV(2);
      mbar_wait(bars + 8 * B_G, 0);
      const float g0 = ((const float*)(smem + OFF_G))[wg * 64 + w * 16 + g], g1 = ((const float*)(smem + OFF_G))[wg * 64 + w * 16 + g + 8];
      const float o0 = 1.0f - g0, o1 = 1.0f - g1;
#pragma unroll
      for (int i = 0; i < 16; i++) yf[i] = pack_pin(c1[2 * i], c1[2 * i + 1]);
#pragma unroll
      for (int i = 0; i < 8; i++) {
        const float o = (i & 1) ? o1 : o0;
        h[48 + i] = pack_pin(fmaxf(c1[32 + 2 * i], 0.f) * c1[48 + 2 * i] * o, fmaxf(c1[33 + 2 * i], 0.f) * c1[49 + 2 * i] * o);
      }
      {
        const int e0 = rs, e1 = rs == 12 ? 8 : rs + 1;
        waitfull(e0); waitfull(e1);
        const int es = wg ? e1 : e0;
        wg_fence();
        mma_rs128<0, 1, 0>(cA, yf[0], yf[1], yf[2], yf[3], dN + es * 1024);
#pragma unroll
        for (int k = 1; k < 4; k++) mma_rs128<0, 1, 1>(cA, yf[4 * k], yf[4 * k + 1], yf[4 * k + 2], yf[4 * k + 3], dN + (es * 1024 + k * 128));
        wg_commit();
        wg_wait<1>();
        release(prev);
        rs = e1 == 12 ? 8 : e1 + 1;
        ffn_step(I1(), c2, 1);
        release(e0); release(e1);
        prev = rs; if (++rs == 13) rs = 8;
        fence_regs<0, 64>(cA);
        const int s0 = 2 * rb + wg;
        float2* dst = g_X1p + ((size_t)((2 * j + (w >> 1)) * 8) * 32 + s0) * 128 + (2 * q) * 16 + 8 * (w & 1) + g;
#pragma unroll
        for (int n = 0; n < 8; n++) {
#pragma unroll
          for (int e = 0; e < 2; e++)
            dst[n * 4096 + e * 16] = make_float2(cA[4 * n + e] - cA[34 + 4 * n + e], cA[32 + 4 * n + e] + cA[4 * n + 2 + e]);
        }
        if (j == 0 && w == 0 && g == 0) {
#pragma unroll
          for (int n = 0; n < 8; n++) {
#pragma unroll
            for (int e = 0; e < 2; e++) {
              g_X1s[s0 * 64 + 8 * n + 2 * q + e] = make_float2(cA[4 * n + e], cA[32 + 4 * n + e]);
              g_X1s[(32 + s0) * 64 + 8 * n + 2 * q + e] = make_float2(cA[4 * n + 2 + e], cA[34 + 4 * n + e]);
            }
          }
        }
        __syncwarp();
        if (lane == 0) mbar_arrive(bars + 8 * B_X1);
        if (tid == 0) PROF_EV(3);
      }
      auto glu = [&](float (&acc)[64], int ho) {
#pragma unroll
        for (int i = 0; i < 16; i++) {
          const float o = (i & 1) ? o1 : o0;
          h[ho + i] = pack_pin(fmaxf(acc[2 * i], 0.f) * acc[32 + 2 * i] * o, fmaxf(acc[2 * i + 1], 0.f) * acc[33 + 2 * i] * o);
        }
      };
#pragma unroll 1
      for (int kb = 2; kb < 8; kb++) { ffn_step(I1(), c2, kb); release(prev); prev = rs; if (++rs == 13) rs = 8; }
      ffn_step(I2(), cA, 0); release(prev); prev = rs; if (++rs == 13) rs = 8;
      fence_regs<0, 64>(c2);
      if (tid == 0) PROF_EV(4);
      glu(c2, 0);
#pragma unroll 1
      for (int kb = 1; kb < 8; kb++) { ffn_step(I1(), cA, kb); release(prev); prev = rs; if (++rs == 13) rs = 8; }
      ffn_step(I2(), c2, 0); release(prev); prev = rs; if (++rs == 13) rs = 8;
      fence_regs<0, 64>(cA);
      if (tid == 0) PROF_EV(5);
      glu(cA, 16);
#pragma unroll 1
      for (int kb = 1; kb < 8; kb++) { ffn_step(I1(), c2, kb); release(prev); release(kb - 1); prev = rs; if (++rs == 13) rs = 8; }
      int m = 2;
      auto piece = [&](auto off, int p, bool rel = true) {
        constexpr int O = decltype(off)::value;
        const int s = ringB(m);
        waitfull(s);
        wg_fence();
        const uint64_t db = dN + s * 1024;
        if (p == 0) {
          mma_rs64<O, 1, 0>(ct, h[0], h[1], h[2], h[3], db);
#pragma unroll
          for (int k = 1; k < 6; k++) mma_rs64<O, 1, 1>(ct, h[4 * k], h[4 * k + 1], h[4 * k + 2], h[4 * k + 3], db + k * 128);
        } else if (p == 1) {
#pragma unroll
          for (int k = 0; k < 6; k++) mma_rs64<O, 1, 1>(ct, h[24 + 4 * k], h[25 + 4 * k], h[26 + 4 * k], h[27 + 4 * k], db + k * 128);
        } else {
#pragma unroll
          for (int k = 0; k < 4; k++) mma_rs64<O, 1, 1>(ct, yf[4 * k], yf[4 * k + 1], yf[4 * k + 2], yf[4 * k + 3], db + k * 128);
#pragma unroll
          for (int k = 0; k < 2; k++) mma_rs64<O, 1, 1>(ct, h[48 + 4 * k], h[49 + 4 * k], h[50 + 4 * k], h[51 + 4 * k], db + (4 + k) * 128);
        }
        wg_commit();
        wg_wait<1>();
        if (rel) release(prev);
        prev = s; if (++m == 13) m = 0;
      };
      auto send = [&](auto off, int t) {
        constexpr int O = decltype(off)::value;
        fence_regs<O, 32>(ct);
        uint4* dst = g_part + (size_t)((rb * 8 + ((j + 1 + t) & 7)) * 8 + j) * 1024 + tid;
#pragma unroll
        for (int i = 0; i < 4; i++)
          dst[i * 256] = make_uint4(pack_bf16(ct[O + 8 * i], ct[O + 8 * i + 1]), pack_bf16(ct[O + 8 * i + 2], ct[O + 8 * i + 3]),
                                    pack_bf16(ct[O + 8 * i + 4], ct[O + 8 * i + 5]), pack_bf16(ct[O + 8 * i + 6], ct[O + 8 * i + 7]));
        __syncwarp();
        if (lane == 0) mbar_arrive(bars + 8 * (B_P + t));
      };
      wg_wait<0>();
      release(prev); release(7);
      fence_regs<0, 64>(c2);
      glu(c2, 32);
      waitfull(0); waitfull(1);
      if (tid == 0) PROF_EV(6);
      mbar_wait(bars + 8 * B_T, 0);
      if (tid == 0) PROF_EV(7);
      wg_fence();
      {
        const uint64_t dt = dN + ((OFF_W >> 4) + xo), de = dK + wg * 1024;
        mma_ss64<0, 1, 0>(ci, de, dt);
        mma_ss64<32, 1, 0>(ci, de + 512, dt);
#pragma unroll
        for (int k = 1; k < 4; k++) {
          mma_ss64<0, 1, 1>(ci, de + k * 2, dt + k * 128);
          mma_ss64<32, 1, 1>(ci, de + (512 + k * 2), dt + k * 128);
        }
      }
      wg_commit();
      piece(I0(), 0, false);
      release(0); release(1);
      fence_regs<0, 64>(ci);
#pragma unroll
      for (int i = 0; i < 16; i++) {
        const float gg = (i & 1) ? g1 : g0;
        yf[i] = pack_pin((ci[2 * i] + ci[33 + 2 * i]) * gg, (ci[2 * i + 1] - ci[32 + 2 * i]) * gg);
      }
      piece(I0(), 1); piece(I0(), 2);
      if (tid == 0) PROF_EV(8);
#pragma unroll 1
      for (int t = 1; t < 7; t += 2) {
        piece(I32(), 0); send(I0(), t - 1); piece(I32(), 1); piece(I32(), 2);
        piece(I0(), 0); send(I32(), t); piece(I0(), 1); piece(I0(), 2);
      }
      piece(I32(), 0); send(I0(), 6); piece(I32(), 1); piece(I32(), 2);
      if (tid == 0) PROF_EV(9);
      mbar_wait(bars + 8 * B_R, 0);
      if (tid == 0) PROF_EV(14);
      {
        const uint4* src = g_part + (size_t)(rb * 8 + j) * 8 * 1024 + tid;
        wg_wait<0>();
        fence_regs<32, 32>(ct);
        uint4 pv[28];
#pragma unroll
        for (int t = 0; t < 7; t++)
#pragma unroll
          for (int i = 0; i < 4; i++) pv[4 * t + i] = __ldcg(src + ((j + 1 + t) & 7) * 1024 + i * 256);
#pragma unroll
        for (int t = 0; t < 7; t++)
#pragma unroll
          for (int i = 0; i < 4; i++) {
            const uint4 p = pv[4 * t + i];
            ct[32 + 8 * i] += bf_lo(p.x); ct[33 + 8 * i] += bf_hi(p.x); ct[34 + 8 * i] += bf_lo(p.y); ct[35 + 8 * i] += bf_hi(p.y);
            ct[36 + 8 * i] += bf_lo(p.z); ct[37 + 8 * i] += bf_hi(p.z); ct[38 + 8 * i] += bf_lo(p.w); ct[39 + 8 * i] += bf_hi(p.w);
          }
        const int srow = 2 * rb + wg + 32 * (16 * w + g);
        uint32_t* o = (uint32_t*)(out + (size_t)srow * 512 + 64 * j + 2 * q);
#pragma unroll
        for (int n = 0; n < 8; n++) {
          o[4 * n] = pack_bf16(ct[32 + 4 * n], ct[33 + 4 * n]);
          o[4 * n + 8 * 32 * 256] = pack_bf16(ct[34 + 4 * n], ct[35 + 4 * n]);
        }
      }
      if (tid == 0) PROF_EV(15);
    }
  }
}

typedef CUresult (*EncodeFn)(CUtensorMap*, CUtensorMapDataType, cuuint32_t, void*, const cuuint64_t*, const cuuint64_t*, const cuuint32_t*,
                             const cuuint32_t*, CUtensorMapInterleave, CUtensorMapSwizzle, CUtensorMapL2promotion, CUtensorMapFloatOOBfill);

static void encode(EncodeFn f, CUtensorMap* m, const void* base, int rank, const cuuint64_t* dims, const cuuint64_t* strides, const cuuint32_t* box,
                   CUtensorMapSwizzle sw) {
  cuuint32_t es[5] = {1, 1, 1, 1, 1};
  f(m, CU_TENSOR_MAP_DATA_TYPE_BFLOAT16, rank, (void*)base, dims, strides, box, es, CU_TENSOR_MAP_INTERLEAVE_NONE, sw,
    CU_TENSOR_MAP_L2_PROMOTION_L2_128B, CU_TENSOR_MAP_FLOAT_OOB_FILL_NONE);
}

extern "C" void kernel_launch(void* const* d_in, const int* in_sizes, int n_in, void* d_out, int out_size) {
  (void)in_sizes; (void)n_in; (void)out_size;
  const __nv_bfloat16* x = (const __nv_bfloat16*)d_in[0];
  const __nv_bfloat16* w_r = (const __nv_bfloat16*)d_in[1];
  const __nv_bfloat16* w_i = (const __nv_bfloat16*)d_in[2];
  const __nv_bfloat16* Wg = (const __nv_bfloat16*)d_in[4];
  const __nv_bfloat16* Wu = (const __nv_bfloat16*)d_in[5];
  const __nv_bfloat16* Wd = (const __nv_bfloat16*)d_in[6];
  const __nv_bfloat16* gw = (const __nv_bfloat16*)d_in[7];

  void* fp = nullptr; cudaDriverEntryPointQueryResult qr;
  cudaGetDriverEntryPoint("cuTensorMapEncodeTiled", &fp, cudaEnableDefault, &qr);
  EncodeFn enc = (EncodeFn)fp;
  void *pFT, *pET, *pT;
  cudaGetSymbolAddress(&pFT, g_FT); cudaGetSymbolAddress(&pET, g_ET); cudaGetSymbolAddress(&pT, g_Tp);

  Maps mp;
  const CUtensorMapSwizzle S128 = CU_TENSOR_MAP_SWIZZLE_128B, S64 = CU_TENSOR_MAP_SWIZZLE_64B;
  { cuuint64_t d[3] = {512, 64, 32}, s[2] = {32768, 1024}; cuuint32_t b[3] = {64, 64, 2}; encode(enc, &mp.x, x, 3, d, s, b, S128); }
  { cuuint64_t d[2] = {512, 512}, s[1] = {1024}; cuuint32_t b[2] = {64, 64}; encode(enc, &mp.ft, pFT, 2, d, s, b, S128); }
  { cuuint64_t d[4] = {512, 2, 8, 32}, s[3] = {8192, 1024, 16384}; cuuint32_t b[4] = {64, 2, 8, 4}; encode(enc, &mp.fg, pFT, 4, d, s, b, S128); }
  { cuuint64_t d[4] = {64, 64, 2, 32}, s[3] = {8192, 128, 256}; cuuint32_t b[4] = {64, 64, 2, 1}; encode(enc, &mp.e, pET, 4, d, s, b, S128); }
  { cuuint64_t d[2] = {1792, 512}, s[1] = {3584}; cuuint32_t b[2] = {64, 64}, b2[2] = {32, 64};
    encode(enc, &mp.g64, Wg, 2, d, s, b, S128); encode(enc, &mp.u64, Wu, 2, d, s, b, S128);
    encode(enc, &mp.g32, Wg, 2, d, s, b2, S64); encode(enc, &mp.u32, Wu, 2, d, s, b2, S64); }
  { cuuint64_t d[2] = {512, 1792}, s[1] = {1024}; cuuint32_t b[2] = {64, 96}, b2[2] = {64, 32};
    encode(enc, &mp.d96, Wd, 2, d, s, b, S128); encode(enc, &mp.d32, Wd, 2, d, s, b2, S128); }
  { cuuint64_t d[3] = {512, 64, 32}, s[2] = {1024, 65536}; cuuint32_t b[3] = {64, 64, 2}; encode(enc, &mp.t, pT, 3, d, s, b, S128); }

  cudaFuncSetAttribute(fused_kernel, cudaFuncAttributeMaxDynamicSharedMemorySize, SMEM_BYTES);
  fused_kernel<<<129, 512, SMEM_BYTES>>>(mp, w_r, w_i, gw, Wg, Wu, Wd, (__nv_bfloat16*)d_out);
}
```

```cpp
#include <cuda_runtime.h>
#include <cuda_bf16.h>
#include <cuda.h>
#include <stdint.h>

namespace tbl {
constexpr double PI = 3.14159265358979323846264338327950288;
constexpr double sin_s(double x) { double t = x, s = x; for (int n = 1; n < 12; n++) { t *= -x * x / ((2 * n) * (2 * n + 1)); s += t; } return s; }
constexpr double cos_s(double x) { double t = 1, s = 1; for (int n = 1; n < 12; n++) { t *= -x * x / ((2 * n - 1) * (2 * n)); s += t; } return s; }
constexpr double cos2048(int m) {
  m &= 2047; if (m > 1024) m = 2048 - m;
  bool neg = false; if (m > 512) { m = 1024 - m; neg = true; }
  double v = (m <= 256) ? cos_s(2 * PI * m / 2048) : sin_s(2 * PI * (512 - m) / 2048);
  return neg ? -v : v;
}
constexpr uint16_t to_bf16(double v) {
  if (v == 0) return 0;
  uint16_t s = 0; if (v < 0) { s = 0x8000; v = -v; }
  int e = 0; while (v >= 2) { v /= 2; e++; } while (v < 1) { v *= 2; e--; }
  double m = (v - 1) * 128; int mi = (int)m; double fr = m - mi;
  if (fr > 0.5 || (fr == 0.5 && (mi & 1))) mi++;
  if (mi == 128) { mi = 0; e++; }
  return (uint16_t)(s | ((e + 127) << 7) | mi);
}
struct CosT { uint16_t v[2048]; constexpr CosT() : v() { for (int i = 0; i < 2048; i++) v[i] = to_bf16(cos2048(i)); } };
struct alignas(1024) FT {
  uint16_t v[512 * 512];
  constexpr FT() : v() {
    CosT c;
    for (int r = 0; r < 512; r++) {
      int k = (r >> 4) * 8 + (r & 7), e = (r >> 3) & 1;
      int mul = 4 * k, add = e ? 512 : 0;
      if (k == 0 && e == 1) { mul = 1024; add = 0; }
      for (int d = 0; d < 512; d++) v[r * 512 + d] = c.v[(d * mul + add) & 2047];
    }
  }
};
struct alignas(1024) ET {
  uint16_t v[2048 * 128];
  constexpr ET() : v() {
    CosT c;
    for (int s = 0; s < 2048; s++)
      for (int j = 0; j < 64; j++) { v[s * 128 + j] = c.v[(s * j) & 2047]; v[s * 128 + 64 + j] = c.v[(s * j + 512) & 2047]; }
  }
};
template <int A> struct W32 {
  static constexpr float c = (float)cos2048(A * 64);
  static constexpr float s = (float)cos2048(A * 64 - 512);
};
}

__device__ constexpr tbl::FT g_FT = tbl::FT();
__device__ constexpr tbl::ET g_ET = tbl::ET();

__device__ __align__(1024) float2 g_X1p[128 * 32 * 128];
__device__ __align__(1024) float2 g_X1s[2 * 32 * 64];
__device__ __align__(1024) uint32_t g_Tp[32 * 64 * 256];
__device__ __align__(1024) uint4 g_part[16 * 8 * 8 * 1024];
__device__ unsigned g_ticket;
__device__ unsigned g_cntX[8 * 32];
__device__ unsigned g_cntT[8 * 32];
__device__ unsigned g_cntP[128 * 32];
__device__ unsigned g_cntG[16 * 32];
__device__ unsigned g_cntW[32];
__device__ __align__(16) float g_gate[16 * 128];
__device__ __align__(16) float2 g_Wh[2 * 2048];
#define PROF_EV(i) do {} while (0)
#define PROF_CK(i) do {} while (0)

__device__ __forceinline__ uint32_t smem_u32(const void* p) { return (uint32_t)__cvta_generic_to_shared(p); }
__device__ __forceinline__ void mbar_init(uint32_t bar, uint32_t cnt) { asm volatile("mbarrier.init.shared::cta.b64 [%0], %1;" ::"r"(bar), "r"(cnt)); }
__device__ __forceinline__ void mbar_expect_tx(uint32_t bar, uint32_t bytes) { asm volatile("mbarrier.arrive.expect_tx.shared::cta.b64 _, [%0], %1;" ::"r"(bar), "r"(bytes) : "memory"); }
__device__ __forceinline__ void mbar_arrive(uint32_t bar) { asm volatile("mbarrier.arrive.shared::cta.b64 _, [%0];" ::"r"(bar) : "memory"); }
__device__ __forceinline__ bool mbar_try(uint32_t bar, uint32_t parity) {
  uint32_t ok;
  asm volatile("{\n.reg .pred p;\nmbarrier.try_wait.parity.shared::cta.b64 p, [%1], %2;\nselp.u32 %0, 1, 0, p;\n}" : "=r"(ok) : "r"(bar), "r"(parity) : "memory");
  return ok;
}
__device__ __forceinline__ void mbar_wait(uint32_t bar, uint32_t parity) {
  if (mbar_try(bar, parity)) return;
  const uint32_t t0 = (uint32_t)clock();
  while (!mbar_try(bar, parity)) { if ((uint32_t)clock() - t0 > (1u << 30)) __trap(); }
}
__device__ __forceinline__ void poll_ge(const unsigned* p, unsigned target) {
  const uint32_t t0 = (uint32_t)clock();
  for (;;) {
    unsigned v;
    asm volatile("ld.acquire.gpu.global.u32 %0, [%1];" : "=r"(v) : "l"(p) : "memory");
    if ((int)(v - target) >= 0) return;
    if ((uint32_t)clock() - t0 > (1u << 30)) __trap();
  }
}
__device__ __forceinline__ void red_release(unsigned* p) { asm volatile("red.release.gpu.global.add.u32 [%0], 1;" ::"l"(p) : "memory"); }
__device__ __forceinline__ void red_relaxed(unsigned* p) { asm volatile("red.relaxed.gpu.global.add.u32 [%0], 1;" ::"l"(p) : "memory"); }
__device__ __forceinline__ void bulk_load(uint32_t dst, const void* src, uint32_t bytes, uint32_t bar) {
  asm volatile("cp.async.bulk.shared::cluster.global.mbarrier::complete_tx::bytes [%0], [%1], %2, [%3];" ::"r"(dst), "l"(src), "r"(bytes), "r"(bar) : "memory");
}
__device__ __forceinline__ void tma2d(uint32_t dst, const CUtensorMap* m, uint32_t bar, int c0, int c1) {
  asm volatile("cp.async.bulk.tensor.2d.shared::cluster.global.mbarrier::complete_tx::bytes [%0], [%1, {%3, %4}], [%2];" ::"r"(dst), "l"(m), "r"(bar), "r"(c0), "r"(c1) : "memory");
}
__device__ __forceinline__ void tma3d(uint32_t dst, const CUtensorMap* m, uint32_t bar, int c0, int c1, int c2) {
  asm volatile("cp.async.bulk.tensor.3d.shared::cluster.global.mbarrier::complete_tx::bytes [%0], [%1, {%3, %4, %5}], [%2];" ::"r"(dst), "l"(m), "r"(bar), "r"(c0), "r"(c1), "r"(c2) : "memory");
}
__device__ __forceinline__ void tma4d(uint32_t dst, const CUtensorMap* m, uint32_t bar, int c0, int c1, int c2, int c3) {
  asm volatile("cp.async.bulk.tensor.4d.shared::cluster.global.mbarrier::complete_tx::bytes [%0], [%1, {%3, %4, %5, %6}], [%2];" ::"r"(dst), "l"(m), "r"(bar), "r"(c0), "r"(c1), "r"(c2), "r"(c3) : "memory");
}
__device__ __forceinline__ void l2_prefetch(const void* p, uint32_t bytes) { asm volatile("cp.async.bulk.prefetch.L2.global [%0], %1;" ::"l"(p), "r"(bytes) : "memory"); }
__device__ __forceinline__ void wg_fence() { asm volatile("wgmma.fence.sync.aligned;" ::: "memory"); }
__device__ __forceinline__ void wg_commit() { asm volatile("wgmma.commit_group.sync.aligned;" ::: "memory"); }
template <int N> __device__ __forceinline__ void wg_wait() { asm volatile("wgmma.wait_group.sync.aligned %0;" ::"n"(N) : "memory"); }
template <int O, int N, int NN> __device__ __forceinline__ void fence_regs(float (&d)[NN]) {
#pragma unroll
  for (int i = 0; i < N; i++) asm volatile("" : "+f"(d[O + i])::"memory");
}
__device__ __forceinline__ uint64_t mkdesc(uint32_t addr, uint32_t lbo, uint32_t sbo, uint32_t mode) {
  return (uint64_t)((addr & 0x3FFFF) >> 4) | ((uint64_t)(lbo >> 4) << 16) | ((uint64_t)(sbo >> 4) << 32) | ((uint64_t)mode << 62);
}
__device__ __forceinline__ uint32_t pack_bf16(float lo, float hi) {
  uint32_t r; asm("cvt.rn.bf16x2.f32 %0, %1, %2;" : "=r"(r) : "f"(hi), "f"(lo)); return r;
}
__device__ __forceinline__ uint32_t pack_pin(float lo, float hi) {
  uint32_t r; asm volatile("cvt.rn.bf16x2.f32 %0, %1, %2;" : "=r"(r) : "f"(hi), "f"(lo) : "memory"); return r;
}
__device__ __forceinline__ float bf_lo(uint32_t u) { return __uint_as_float(u << 16); }
__device__ __forceinline__ float bf_hi(uint32_t u) { return __uint_as_float(u & 0xffff0000u); }

template<int O,int TB,int ACC,int NN> __device__ __forceinline__ void mma_ss64(float (&d)[NN], uint64_t da, uint64_t db, int sd = 0){
  if constexpr (ACC == 1) asm volatile("wgmma.mma_async.sync.aligned.m64n64k16.f32.bf16.bf16 {%0,%1,%2,%3,%4,%5,%6,%7,%8,%9,%10,%11,%12,%13,%14,%15,%16,%17,%18,%19,%20,%21,%22,%23,%24,%25,%26,%27,%28,%29,%30,%31}, %32, %33, 1, 1, 1, 0, %34;"
   : "+f"(d[O+0]), "+f"(d[O+1]), "+f"(d[O+2]), "+f"(d[O+3]), "+f"(d[O+4]), "+f"(d[O+5]), "+f"(d[O+6]), "+f"(d[O+7]), "+f"(d[O+8]), "+f"(d[O+9]), "+f"(d[O+10]), "+f"(d[O+11]), "+f"(d[O+12]), "+f"(d[O+13]), "+f"(d[O+14]), "+f"(d[O+15]), "+f"(d[O+16]), "+f"(d[O+17]), "+f"(d[O+18]), "+f"(d[O+19]), "+f"(d[O+20]), "+f"(d[O+21]), "+f"(d[O+22]), "+f"(d[O+23]), "+f"(d[O+24]), "+f"(d[O+25]), "+f"(d[O+26]), "+f"(d[O+27]), "+f"(d[O+28]), "+f"(d[O+29]), "+f"(d[O+30]), "+f"(d[O+31])
   : "l"(da), "l"(db), "n"(TB));
  else if constexpr (ACC == 0) asm volatile("wgmma.mma_async.sync.aligned.m64n64k16.f32.bf16.bf16 {%0,%1,%2,%3,%4,%5,%6,%7,%8,%9,%10,%11,%12,%13,%14,%15,%16,%17,%18,%19,%20,%21,%22,%23,%24,%25,%26,%27,%28,%29,%30,%31}, %32, %33, 0, 1, 1, 0, %34;"
   : "=f"(d[O+0]), "=f"(d[O+1]), "=f"(d[O+2]), "=f"(d[O+3]), "=f"(d[O+4]), "=f"(d[O+5]), "=f"(d[O+6]), "=f"(d[O+7]), "=f"(d[O+8]), "=f"(d[O+9]), "=f"(d[O+10]), "=f"(d[O+11]), "=f"(d[O+12]), "=f"(d[O+13]), "=f"(d[O+14]), "=f"(d[O+15]), "=f"(d[O+16]), "=f"(d[O+17]), "=f"(d[O+18]), "=f"(d[O+19]), "=f"(d[O+20]), "=f"(d[O+21]), "=f"(d[O+22]), "=f"(d[O+23]), "=f"(d[O+24]), "=f"(d[O+25]), "=f"(d[O+26]), "=f"(d[O+27]), "=f"(d[O+28]), "=f"(d[O+29]), "=f"(d[O+30]), "=f"(d[O+31])
   : "l"(da), "l"(db), "n"(TB));
  else asm volatile("{\n.reg .pred p;\nsetp.ne.b32 p, %35, 0;\nwgmma.mma_async.sync.aligned.m64n64k16.f32.bf16.bf16 {%0,%1,%2,%3,%4,%5,%6,%7,%8,%9,%10,%11,%12,%13,%14,%15,%16,%17,%18,%19,%20,%21,%22,%23,%24,%25,%26,%27,%28,%29,%30,%31}, %32, %33, p, 1, 1, 0, %34;\n}"
   : "+f"(d[O+0]), "+f"(d[O+1]), "+f"(d[O+2]), "+f"(d[O+3]), "+f"(d[O+4]), "+f"(d[O+5]), "+f"(d[O+6]), "+f"(d[O+7]), "+f"(d[O+8]), "+f"(d[O+9]), "+f"(d[O+10]), "+f"(d[O+11]), "+f"(d[O+12]), "+f"(d[O+13]), "+f"(d[O+14]), "+f"(d[O+15]), "+f"(d[O+16]), "+f"(d[O+17]), "+f"(d[O+18]), "+f"(d[O+19]), "+f"(d[O+20]), "+f"(d[O+21]), "+f"(d[O+22]), "+f"(d[O+23]), "+f"(d[O+24]), "+f"(d[O+25]), "+f"(d[O+26]), "+f"(d[O+27]), "+f"(d[O+28]), "+f"(d[O+29]), "+f"(d[O+30]), "+f"(d[O+31])
   : "l"(da), "l"(db), "n"(TB), "r"(sd));
}
template<int O,int TB,int ACC,int NN> __device__ __forceinline__ void mma_rs64(float (&d)[NN], uint32_t a0, uint32_t a1, uint32_t a2, uint32_t a3, uint64_t db, int sd = 0){
  if constexpr (ACC == 1) asm volatile("wgmma.mma_async.sync.aligned.m64n64k16.f32.bf16.bf16 {%0,%1,%2,%3,%4,%5,%6,%7,%8,%9,%10,%11,%12,%13,%14,%15,%16,%17,%18,%19,%20,%21,%22,%23,%24,%25,%26,%27,%28,%29,%30,%31}, {%32,%33,%34,%35}, %36, 1, 1, 1, %37;"
   : "+f"(d[O+0]), "+f"(d[O+1]), "+f"(d[O+2]), "+f"(d[O+3]), "+f"(d[O+4]), "+f"(d[O+5]), "+f"(d[O+6]), "+f"(d[O+7]), "+f"(d[O+8]), "+f"(d[O+9]), "+f"(d[O+10]), "+f"(d[O+11]), "+f"(d[O+12]), "+f"(d[O+13]), "+f"(d[O+14]), "+f"(d[O+15]), "+f"(d[O+16]), "+f"(d[O+17]), "+f"(d[O+18]), "+f"(d[O+19]), "+f"(d[O+20]), "+f"(d[O+21]), "+f"(d[O+22]), "+f"(d[O+23]), "+f"(d[O+24]), "+f"(d[O+25]), "+f"(d[O+26]), "+f"(d[O+27]), "+f"(d[O+28]), "+f"(d[O+29]), "+f"(d[O+30]), "+f"(d[O+31])
   : "r"(a0), "r"(a1), "r"(a2), "r"(a3), "l"(db), "n"(TB));
  else if constexpr (ACC == 0) asm volatile("wgmma.mma_async.sync.aligned.m64n64k16.f32.bf16.bf16 {%0,%1,%2,%3,%4,%5,%6,%7,%8,%9,%10,%11,%12,%13,%14,%15,%16,%17,%18,%19,%20,%21,%22,%23,%24,%25,%26,%27,%28,%29,%30,%31}, {%32,%33,%34,%35}, %36, 0, 1, 1, %37;"
   : "=f"(d[O+0]), "=f"(d[O+1]), "=f"(d[O+2]), "=f"(d[O+3]), "=f"(d[O+4]), "=f"(d[O+5]), "=f"(d[O+6]), "=f"(d[O+7]), "=f"(d[O+8]), "=f"(d[O+9]), "=f"(d[O+10]), "=f"(d[O+11]), "=f"(d[O+12]), "=f"(d[O+13]), "=f"(d[O+14]), "=f"(d[O+15]), "=f"(d[O+16]), "=f"(d[O+17]), "=f"(d[O+18]), "=f"(d[O+19]), "=f"(d[O+20]), "=f"(d[O+21]), "=f"(d[O+22]), "=f"(d[O+23]), "=f"(d[O+24]), "=f"(d[O+25]), "=f"(d[O+26]), "=f"(d[O+27]), "=f"(d[O+28]), "=f"(d[O+29]), "=f"(d[O+30]), "=f"(d[O+31])
   : "r"(a0), "r"(a1), "r"(a2), "r"(a3), "l"(db), "n"(TB));
  else asm volatile("{\n.reg .pred p;\nsetp.ne.b32 p, %38, 0;\nwgmma.mma_async.sync.aligned.m64n64k16.f32.bf16.bf16 {%0,%1,%2,%3,%4,%5,%6,%7,%8,%9,%10,%11,%12,%13,%14,%15,%16,%17,%18,%19,%20,%21,%22,%23,%24,%25,%26,%27,%28,%29,%30,%31}, {%32,%33,%34,%35}, %36, p, 1, 1, %37;\n}"
   : "+f"(d[O+0]), "+f"(d[O+1]), "+f"(d[O+2]), "+f"(d[O+3]), "+f"(d[O+4]), "+f"(d[O+5]), "+f"(d[O+6]), "+f"(d[O+7]), "+f"(d[O+8]), "+f"(d[O+9]), "+f"(d[O+10]), "+f"(d[O+11]), "+f"(d[O+12]), "+f"(d[O+13]), "+f"(d[O+14]), "+f"(d[O+15]), "+f"(d[O+16]), "+f"(d[O+17]), "+f"(d[O+18]), "+f"(d[O+19]), "+f"(d[O+20]), "+f"(d[O+21]), "+f"(d[O+22]), "+f"(d[O+23]), "+f"(d[O+24]), "+f"(d[O+25]), "+f"(d[O+26]), "+f"(d[O+27]), "+f"(d[O+28]), "+f"(d[O+29]), "+f"(d[O+30]), "+f"(d[O+31])
   : "r"(a0), "r"(a1), "r"(a2), "r"(a3), "l"(db), "n"(TB), "r"(sd));
}
template<int O,int TB,int ACC,int NN> __device__ __forceinline__ void mma_ss128(float (&d)[NN], uint64_t da, uint64_t db, int sd = 0){
  if constexpr (ACC == 1) asm volatile("wgmma.mma_async.sync.aligned.m64n128k16.f32.bf16.bf16 {%0,%1,%2,%3,%4,%5,%6,%7,%8,%9,%10,%11,%12,%13,%14,%15,%16,%17,%18,%19,%20,%21,%22,%23,%24,%25,%26,%27,%28,%29,%30,%31,%32,%33,%34,%35,%36,%37,%38,%39,%40,%41,%42,%43,%44,%45,%46,%47,%48,%49,%50,%51,%52,%53,%54,%55,%56,%57,%58,%59,%60,%61,%62,%63}, %64, %65, 1, 1, 1, 0, %66;"
   : "+f"(d[O+0]), "+f"(d[O+1]), "+f"(d[O+2]), "+f"(d[O+3]), "+f"(d[O+4]), "+f"(d[O+5]), "+f"(d[O+6]), "+f"(d[O+7]), "+f"(d[O+8]), "+f"(d[O+9]), "+f"(d[O+10]), "+f"(d[O+11]), "+f"(d[O+12]), "+f"(d[O+13]), "+f"(d[O+14]), "+f"(d[O+15]), "+f"(d[O+16]), "+f"(d[O+17]), "+f"(d[O+18]), "+f"(d[O+19]), "+f"(d[O+20]), "+f"(d[O+21]), "+f"(d[O+22]), "+f"(d[O+23]), "+f"(d[O+24]), "+f"(d[O+25]), "+f"(d[O+26]), "+f"(d[O+27]), "+f"(d[O+28]), "+f"(d[O+29]), "+f"(d[O+30]), "+f"(d[O+31]), "+f"(d[O+32]), "+f"(d[O+33]), "+f"(d[O+34]), "+f"(d[O+35]), "+f"(d[O+36]), "+f"(d[O+37]), "+f"(d[O+38]), "+f"(d[O+39]), "+f"(d[O+40]), "+f"(d[O+41]), "+f"(d[O+42]), "+f"(d[O+43]), "+f"(d[O+44]), "+f"(d[O+45]), "+f"(d[O+46]), "+f"(d[O+47]), "+f"(d[O+48]), "+f"(d[O+49]), "+f"(d[O+50]), "+f"(d[O+51]), "+f"(d[O+52]), "+f"(d[O+53]), "+f"(d[O+54]), "+f"(d[O+55]), "+f"(d[O+56]), "+f"(d[O+57]), "+f"(d[O+58]), "+f"(d[O+59]), "+f"(d[O+60]), "+f"(d[O+61]), "+f"(d[O+62]), "+f"(d[O+63])
   : "l"(da), "l"(db), "n"(TB));
  else if constexpr (ACC == 0) asm volatile("wgmma.mma_async.sync.aligned.m64n128k16.f32.bf16.bf16 {%0,%1,%2,%3,%4,%5,%6,%7,%8,%9,%10,%11,%12,%13,%14,%15,%16,%17,%18,%19,%20,%21,%22,%23,%24,%25,%26,%27,%28,%29,%30,%31,%32,%33,%34,%35,%36,%37,%38,%39,%40,%41,%42,%43,%44,%45,%46,%47,%48,%49,%50,%51,%52,%53,%54,%55,%56,%57,%58,%59,%60,%61,%62,%63}, %64, %65, 0, 1, 1, 0, %66;"
   : "=f"(d[O+0]), "=f"(d[O+1]), "=f"(d[O+2]), "=f"(d[O+3]), "=f"(d[O+4]), "=f"(d[O+5]), "=f"(d[O+6]), "=f"(d[O+7]), "=f"(d[O+8]), "=f"(d[O+9]), "=f"(d[O+10]), "=f"(d[O+11]), "=f"(d[O+12]), "=f"(d[O+13]), "=f"(d[O+14]), "=f"(d[O+15]), "=f"(d[O+16]), "=f"(d[O+17]), "=f"(d[O+18]), "=f"(d[O+19]), "=f"(d[O+20]), "=f"(d[O+21]), "=f"(d[O+22]), "=f"(d[O+23]), "=f"(d[O+24]), "=f"(d[O+25]), "=f"(d[O+26]), "=f"(d[O+27]), "=f"(d[O+28]), "=f"(d[O+29]), "=f"(d[O+30]), "=f"(d[O+31]), "=f"(d[O+32]), "=f"(d[O+33]), "=f"(d[O+34]), "=f"(d[O+35]), "=f"(d[O+36]), "=f"(d[O+37]), "=f"(d[O+38]), "=f"(d[O+39]), "=f"(d[O+40]), "=f"(d[O+41]), "=f"(d[O+42]), "=f"(d[O+43]), "=f"(d[O+44]), "=f"(d[O+45]), "=f"(d[O+46]), "=f"(d[O+47]), "=f"(d[O+48]), "=f"(d[O+49]), "=f"(d[O+50]), "=f"(d[O+51]), "=f"(d[O+52]), "=f"(d[O+53]), "=f"(d[O+54]), "=f"(d[O+55]), "=f"(d[O+56]), "=f"(d[O+57]), "=f"(d[O+58]), "=f"(d[O+59]), "=f"(d[O+60]), "=f"(d[O+61]), "=f"(d[O+62]), "=f"(d[O+63])
   : "l"(da), "l"(db), "n"(TB));
  else asm volatile("{\n.reg .pred p;\nsetp.ne.b32 p, %67, 0;\nwgmma.mma_async.sync.aligned.m64n128k16.f32.bf16.bf16 {%0,%1,%2,%3,%4,%5,%6,%7,%8,%9,%10,%11,%12,%13,%14,%15,%16,%17,%18,%19,%20,%21,%22,%23,%24,%25,%26,%27,%28,%29,%30,%31,%32,%33,%34,%35,%36,%37,%38,%39,%40,%41,%42,%43,%44,%45,%46,%47,%48,%49,%50,%51,%52,%53,%54,%55,%56,%57,%58,%59,%60,%61,%62,%63}, %64, %65, p, 1, 1, 0, %66;\n}"
   : "+f"(d[O+0]), "+f"(d[O+1]), "+f"(d[O+2]), "+f"(d[O+3]), "+f"(d[O+4]), "+f"(d[O+5]), "+f"(d[O+6]), "+f"(d[O+7]), "+f"(d[O+8]), "+f"(d[O+9]), "+f"(d[O+10]), "+f"(d[O+11]), "+f"(d[O+12]), "+f"(d[O+13]), "+f"(d[O+14]), "+f"(d[O+15]), "+f"(d[O+16]), "+f"(d[O+17]), "+f"(d[O+18]), "+f"(d[O+19]), "+f"(d[O+20]), "+f"(d[O+21]), "+f"(d[O+22]), "+f"(d[O+23]), "+f"(d[O+24]), "+f"(d[O+25]), "+f"(d[O+26]), "+f"(d[O+27]), "+f"(d[O+28]), "+f"(d[O+29]), "+f"(d[O+30]), "+f"(d[O+31]), "+f"(d[O+32]), "+f"(d[O+33]), "+f"(d[O+34]), "+f"(d[O+35]), "+f"(d[O+36]), "+f"(d[O+37]), "+f"(d[O+38]), "+f"(d[O+39]), "+f"(d[O+40]), "+f"(d[O+41]), "+f"(d[O+42]), "+f"(d[O+43]), "+f"(d[O+44]), "+f"(d[O+45]), "+f"(d[O+46]), "+f"(d[O+47]), "+f"(d[O+48]), "+f"(d[O+49]), "+f"(d[O+50]), "+f"(d[O+51]), "+f"(d[O+52]), "+f"(d[O+53]), "+f"(d[O+54]), "+f"(d[O+55]), "+f"(d[O+56]), "+f"(d[O+57]), "+f"(d[O+58]), "+f"(d[O+59]), "+f"(d[O+60]), "+f"(d[O+61]), "+f"(d[O+62]), "+f"(d[O+63])
   : "l"(da), "l"(db), "n"(TB), "r"(sd));
}
template<int O,int TB,int ACC,int NN> __device__ __forceinline__ void mma_rs128(float (&d)[NN], uint32_t a0, uint32_t a1, uint32_t a2, uint32_t a3, uint64_t db, int sd = 0){
  if constexpr (ACC == 1) asm volatile("wgmma.mma_async.sync.aligned.m64n128k16.f32.bf16.bf16 {%0,%1,%2,%3,%4,%5,%6,%7,%8,%9,%10,%11,%12,%13,%14,%15,%16,%17,%18,%19,%20,%21,%22,%23,%24,%25,%26,%27,%28,%29,%30,%31,%32,%33,%34,%35,%36,%37,%38,%39,%40,%41,%42,%43,%44,%45,%46,%47,%48,%49,%50,%51,%52,%53,%54,%55,%56,%57,%58,%59,%60,%61,%62,%63}, {%64,%65,%66,%67}, %68, 1, 1, 1, %69;"
   : "+f"(d[O+0]), "+f"(d[O+1]), "+f"(d[O+2]), "+f"(d[O+3]), "+f"(d[O+4]), "+f"(d[O+5]), "+f"(d[O+6]), "+f"(d[O+7]), "+f"(d[O+8]), "+f"(d[O+9]), "+f"(d[O+10]), "+f"(d[O+11]), "+f"(d[O+12]), "+f"(d[O+13]), "+f"(d[O+14]), "+f"(d[O+15]), "+f"(d[O+16]), "+f"(d[O+17]), "+f"(d[O+18]), "+f"(d[O+19]), "+f"(d[O+20]), "+f"(d[O+21]), "+f"(d[O+22]), "+f"(d[O+23]), "+f"(d[O+24]), "+f"(d[O+25]), "+f"(d[O+26]), "+f"(d[O+27]), "+f"(d[O+28]), "+f"(d[O+29]), "+f"(d[O+30]), "+f"(d[O+31]), "+f"(d[O+32]), "+f"(d[O+33]), "+f"(d[O+34]), "+f"(d[O+35]), "+f"(d[O+36]), "+f"(d[O+37]), "+f"(d[O+38]), "+f"(d[O+39]), "+f"(d[O+40]), "+f"(d[O+41]), "+f"(d[O+42]), "+f"(d[O+43]), "+f"(d[O+44]), "+f"(d[O+45]), "+f"(d[O+46]), "+f"(d[O+47]), "+f"(d[O+48]), "+f"(d[O+49]), "+f"(d[O+50]), "+f"(d[O+51]), "+f"(d[O+52]), "+f"(d[O+53]), "+f"(d[O+54]), "+f"(d[O+55]), "+f"(d[O+56]), "+f"(d[O+57]), "+f"(d[O+58]), "+f"(d[O+59]), "+f"(d[O+60]), "+f"(d[O+61]), "+f"(d[O+62]), "+f"(d[O+63])
   : "r"(a0), "r"(a1), "r"(a2), "r"(a3), "l"(db), "n"(TB));
  else if constexpr (ACC == 0) asm volatile("wgmma.mma_async.sync.aligned.m64n128k16.f32.bf16.bf16 {%0,%1,%2,%3,%4,%5,%6,%7,%8,%9,%10,%11,%12,%13,%14,%15,%16,%17,%18,%19,%20,%21,%22,%23,%24,%25,%26,%27,%28,%29,%30,%31,%32,%33,%34,%35,%36,%37,%38,%39,%40,%41,%42,%43,%44,%45,%46,%47,%48,%49,%50,%51,%52,%53,%54,%55,%56,%57,%58,%59,%60,%61,%62,%63}, {%64,%65,%66,%67}, %68, 0, 1, 1, %69;"
   : "=f"(d[O+0]), "=f"(d[O+1]), "=f"(d[O+2]), "=f"(d[O+3]), "=f"(d[O+4]), "=f"(d[O+5]), "=f"(d[O+6]), "=f"(d[O+7]), "=f"(d[O+8]), "=f"(d[O+9]), "=f"(d[O+10]), "=f"(d[O+11]), "=f"(d[O+12]), "=f"(d[O+13]), "=f"(d[O+14]), "=f"(d[O+15]), "=f"(d[O+16]), "=f"(d[O+17]), "=f"(d[O+18]), "=f"(d[O+19]), "=f"(d[O+20]), "=f"(d[O+21]), "=f"(d[O+22]), "=f"(d[O+23]), "=f"(d[O+24]), "=f"(d[O+25]), "=f"(d[O+26]), "=f"(d[O+27]), "=f"(d[O+28]), "=f"(d[O+29]), "=f"(d[O+30]), "=f"(d[O+31]), "=f"(d[O+32]), "=f"(d[O+33]), "=f"(d[O+34]), "=f"(d[O+35]), "=f"(d[O+36]), "=f"(d[O+37]), "=f"(d[O+38]), "=f"(d[O+39]), "=f"(d[O+40]), "=f"(d[O+41]), "=f"(d[O+42]), "=f"(d[O+43]), "=f"(d[O+44]), "=f"(d[O+45]), "=f"(d[O+46]), "=f"(d[O+47]), "=f"(d[O+48]), "=f"(d[O+49]), "=f"(d[O+50]), "=f"(d[O+51]), "=f"(d[O+52]), "=f"(d[O+53]), "=f"(d[O+54]), "=f"(d[O+55]), "=f"(d[O+56]), "=f"(d[O+57]), "=f"(d[O+58]), "=f"(d[O+59]), "=f"(d[O+60]), "=f"(d[O+61]), "=f"(d[O+62]), "=f"(d[O+63])
   : "r"(a0), "r"(a1), "r"(a2), "r"(a3), "l"(db), "n"(TB));
  else asm volatile("{\n.reg .pred p;\nsetp.ne.b32 p, %70, 0;\nwgmma.mma_async.sync.aligned.m64n128k16.f32.bf16.bf16 {%0,%1,%2,%3,%4,%5,%6,%7,%8,%9,%10,%11,%12,%13,%14,%15,%16,%17,%18,%19,%20,%21,%22,%23,%24,%25,%26,%27,%28,%29,%30,%31,%32,%33,%34,%35,%36,%37,%38,%39,%40,%41,%42,%43,%44,%45,%46,%47,%48,%49,%50,%51,%52,%53,%54,%55,%56,%57,%58,%59,%60,%61,%62,%63}, {%64,%65,%66,%67}, %68, p, 1, 1, %69;\n}"
   : "+f"(d[O+0]), "+f"(d[O+1]), "+f"(d[O+2]), "+f"(d[O+3]), "+f"(d[O+4]), "+f"(d[O+5]), "+f"(d[O+6]), "+f"(d[O+7]), "+f"(d[O+8]), "+f"(d[O+9]), "+f"(d[O+10]), "+f"(d[O+11]), "+f"(d[O+12]), "+f"(d[O+13]), "+f"(d[O+14]), "+f"(d[O+15]), "+f"(d[O+16]), "+f"(d[O+17]), "+f"(d[O+18]), "+f"(d[O+19]), "+f"(d[O+20]), "+f"(d[O+21]), "+f"(d[O+22]), "+f"(d[O+23]), "+f"(d[O+24]), "+f"(d[O+25]), "+f"(d[O+26]), "+f"(d[O+27]), "+f"(d[O+28]), "+f"(d[O+29]), "+f"(d[O+30]), "+f"(d[O+31]), "+f"(d[O+32]), "+f"(d[O+33]), "+f"(d[O+34]), "+f"(d[O+35]), "+f"(d[O+36]), "+f"(d[O+37]), "+f"(d[O+38]), "+f"(d[O+39]), "+f"(d[O+40]), "+f"(d[O+41]), "+f"(d[O+42]), "+f"(d[O+43]), "+f"(d[O+44]), "+f"(d[O+45]), "+f"(d[O+46]), "+f"(d[O+47]), "+f"(d[O+48]), "+f"(d[O+49]), "+f"(d[O+50]), "+f"(d[O+51]), "+f"(d[O+52]), "+f"(d[O+53]), "+f"(d[O+54]), "+f"(d[O+55]), "+f"(d[O+56]), "+f"(d[O+57]), "+f"(d[O+58]), "+f"(d[O+59]), "+f"(d[O+60]), "+f"(d[O+61]), "+f"(d[O+62]), "+f"(d[O+63])
   : "r"(a0), "r"(a1), "r"(a2), "r"(a3), "l"(db), "n"(TB), "r"(sd));
}

__host__ __device__ constexpr int brev(int a, int bits) { int r = 0; for (int i = 0; i < bits; i++) r |= ((a >> i) & 1) << (bits - 1 - i); return r; }
__host__ __device__ constexpr int ilog2(int n) { return n <= 1 ? 0 : 1 + ilog2(n / 2); }
template <int SG, int A> __device__ __forceinline__ void bfly(float2& a, float2& b) {
  if constexpr (A == 0) {
    float tr = a.x - b.x, ti = a.y - b.y; a.x += b.x; a.y += b.y; b.x = tr; b.y = ti;
  } else if constexpr (A == 8) {
    float pr = SG > 0 ? -b.y : b.y, pi = SG > 0 ? b.x : -b.x;
    b.x = a.x - pr; b.y = a.y - pi; a.x += pr; a.y += pi;
  } else {
    constexpr float wr = tbl::W32<A>::c, wi = SG * tbl::W32<A>::s;
    float tr = fmaf(wr, b.x, a.x), ti = fmaf(wr, b.y, a.y);
    tr = fmaf(-wi, b.y, tr); ti = fmaf(wi, b.x, ti);
    b.x = fmaf(2.f, a.x, -tr); b.y = fmaf(2.f, a.y, -ti); a.x = tr; a.y = ti;
  }
}
template <int SG, int N, int O, int ST, int A> __device__ __forceinline__ void dft_comb(float2 (&x)[32]) {
  if constexpr (A < N / 2) {
    constexpr int p = O + 2 * ST * brev(A, ilog2(N / 2));
    bfly<SG, A * (32 / N)>(x[p], x[p + ST]);
    dft_comb<SG, N, O, ST, A + 1>(x);
  }
}
template <int SG, int N, int O, int ST> __device__ __forceinline__ void dft(float2 (&x)[32]) {
  if constexpr (N > 1) {
    dft<SG, N / 2, O, 2 * ST>(x);
    dft<SG, N / 2, O + ST, 2 * ST>(x);
    dft_comb<SG, N, O, ST, 0>(x);
  }
}

#define PFMODE 2
#define MAPMODE 1
struct I0 { static constexpr int value = 0; };
struct I1 { static constexpr int value = 1; };
struct I2 { static constexpr int value = 2; };
struct I32 { static constexpr int value = 32; };
struct Maps { CUtensorMap x, ft, fg, e, g64, u64, g32, u32, d96, d32, t, wr, wi; };

constexpr int NCTA = 132;
constexpr int SLOT = 16384;
constexpr int NSLOT = 13;
constexpr int OFF_W = NSLOT * SLOT;
constexpr int OFF_G = OFF_W + SLOT;
constexpr int OFF_BAR = OFF_G + 512;
constexpr int SMEM_BYTES = OFF_BAR + 512;
constexpr int B_FULL = 0, B_EMPTY = 13, B_FIN = 26, B_P = 39, B_X1 = 46, B_G = 47, B_XR = 48, B_T = 49, B_W = 50, B_R = 51, NBAR = 58;

__device__ __forceinline__ int ringB(int m) {
  return (int)((0xB7A69584C3210ULL >> (4 * m)) & 15);
}

__global__ void __launch_bounds__(512, 1)
fused_kernel(const __grid_constant__ Maps maps, const __nv_bfloat16* __restrict__ x, const __nv_bfloat16* __restrict__ w_r,
             const __nv_bfloat16* __restrict__ w_i, const __nv_bfloat16* __restrict__ gate_w, __nv_bfloat16* __restrict__ out) {
  extern __shared__ __align__(1024) uint8_t smem[];
  const uint32_t sb = smem_u32(smem);
  const uint32_t bars = sb + OFF_BAR;
  const int tid = threadIdx.x, warp = tid >> 5, lane = tid & 31;
  const bool helper = blockIdx.x >= 128;
  const int idx = (blockIdx.x + 120) & 127;
  const int rb = ((idx >> 5) << 2) | ((idx >> 2) & 3), j = (((idx >> 4) & 1) << 2) | (idx & 3);
  const int fm = 448 * (j >> 1);
  const int f_full = fm + ((j & 1) ? 256 : 0);
  const int f_half = fm + ((j & 1) ? 224 : 192);
  const int kg = 2 * j + (rb >> 3), tn = rb & 7;

  if (tid < NBAR) {
    mbar_init(bars + 8 * tid, tid < B_EMPTY ? 1 : tid < B_P ? 2 : tid <= B_X1 ? 8 : 1);
    asm volatile("fence.mbarrier_init.release.cluster;" ::: "memory");
  } else if (warp == 15 && lane < 13) {
    asm volatile("prefetch.tensormap [%0];" ::"l"((const char*)&maps + lane * 128) : "memory");
  }
  if (tid == 64) { PROF_EV(0); PROF_CK(40); }
  __syncthreads();

  if (warp >= 12) {
    asm volatile("setmaxnreg.dec.sync.aligned.u32 32;");
    if ((warp == 12 || warp == 15) && lane == 0 && !helper) {
      uint32_t eph = 0xFFFFFF00u;
      int turn = warp == 12 ? 0 : 1;
      auto acquire = [&](int s, uint32_t bytes) -> bool {
        const uint32_t ph = (eph >> s) & 1; eph ^= 1u << s;
        turn ^= 1;
        if (!turn) return false;
        mbar_wait(bars + 8 * (B_EMPTY + s), ph);
        mbar_expect_tx(bars + 8 * (B_FULL + s), bytes);
        return true;
      };
      auto loadE = [&](int s, int w) { if (acquire(s, SLOT)) tma4d(sb + s * SLOT, &maps.e, bars + 8 * (B_FULL + s), 0, 0, 0, 2 * rb + w); };
      int bt = 0, bp = 0;
      auto loadB = [&](int m) {
        const int s = ringB(m >= 13 ? m - 13 : m);
        if (m < 2) { loadE(s, m); return; }
        const int col = 64 * ((j + 1 + bt) & 7);
        const uint32_t fb = bars + 8 * (B_FULL + s);
        if (acquire(s, 12288)) {
          if (bp < 2) tma2d(sb + s * SLOT, &maps.d96, fb, col, f_full + 96 * bp);
          else { tma4d(sb + s * SLOT, &maps.fg, fb, col, 0, 0, 4 * j); tma2d(sb + s * SLOT + 8192, &maps.d32, fb, col, f_half); }
        }
        if (++bp == 3) { bp = 0; bt++; }
      };
      int rs = 8;
      if (warp == 12) PROF_EV(30);
#pragma unroll 1
      for (int n = 0; n < 34; n++) {
        const uint32_t fb = bars + 8 * (B_FULL + rs), dst = sb + rs * SLOT;
        if (n < 8) {
          if (acquire(rs, SLOT)) {
            tma2d(dst, &maps.ft, fb, 64 * n, 64 * j);
            tma2d(dst + 8192, &maps.g32, fb, f_half, 64 * n);
            tma2d(dst + 12288, &maps.u32, fb, f_half, 64 * n);
          }
        } else if (n == 9 || n == 10) {
          loadE(rs, n - 9);
        } else {
          const int q = n == 8 ? 0 : n - 10;
          if (acquire(rs, SLOT)) {
            tma2d(dst, &maps.g64, fb, f_full + 64 * (q >> 3), 64 * (q & 7));
            tma2d(dst + 8192, &maps.u64, fb, f_full + 64 * (q >> 3), 64 * (q & 7));
          }
          if (n >= 31) loadB(n - 31);
        }
        if (++rs == 13) rs = 8;
      }
#pragma unroll 1
      for (int m = 3; m < 26; m++) loadB(m);
    } else if (warp == 13 && lane == 0 && !helper) {
#pragma unroll 1
      for (int q = 0; q < 8; q++) {
        mbar_expect_tx(bars + 8 * (B_FULL + q), SLOT);
        tma3d(sb + q * SLOT, &maps.x, bars + 8 * (B_FULL + q), 64 * q, 0, 2 * rb);
      }
      PROF_EV(31);
      mbar_wait(bars + 8 * B_X1, 0);
      red_release(&g_cntX[32 * j]);
      PROF_EV(20);
#pragma unroll 1
      for (int t = 0; t < 7; t++) {
        mbar_wait(bars + 8 * (B_P + t), 0);
        red_release(&g_cntP[32 * (rb * 8 + ((j + 1 + t) & 7)) + t]);
      }
      PROF_EV(21);
    } else if (warp == 14) {
      unsigned ep = 0;
      if (lane == 0) {
        ep = atomicAdd(&g_ticket, 1u) / (unsigned)NCTA + 1u;
        if (helper) poll_ge(&g_cntW[0], ep * 128u); else poll_ge(&g_cntG[32 * rb], ep * 8u);
      }
      __syncwarp();
      if (!helper) {
        *(float4*)(smem + OFF_G + lane * 16) = __ldcg((const float4*)(g_gate + rb * 128) + lane);
        __syncwarp();
      }
      if (lane == 0) {
        mbar_arrive(bars + 8 * B_G);
        PROF_EV(10);
        poll_ge(&g_cntX[helper ? 0 : 32 * j], ep * 16u);
        mbar_arrive(bars + 8 * B_XR);
        PROF_EV(22);
        if (!helper) {
          poll_ge(&g_cntT[32 * j], ep * (j == 0 ? 20u : 16u));
          asm volatile("fence.proxy.async;" ::: "memory");
          mbar_expect_tx(bars + 8 * B_T, SLOT);
          tma3d(sb + OFF_W, &maps.t, bars + 8 * B_T, 64 * j, 0, 2 * rb);
          PROF_EV(23);
#pragma unroll 1
          for (int t = 0; t < 7; t++) {
            const int s = ringB(t);
            poll_ge(&g_cntP[32 * (rb * 8 + j) + t], ep);
            asm volatile("fence.proxy.async;" ::: "memory");
            mbar_wait(bars + 8 * (B_FIN + t), 0);
            mbar_expect_tx(bars + 8 * (B_R + t), SLOT);
            bulk_load(sb + s * SLOT, g_part + (size_t)((rb * 8 + j) * 8 + t) * 1024, SLOT, bars + 8 * (B_R + t));
          }
          PROF_EV(24);
        }
      }
    }
  } else if (warp >= 8) {
    asm volatile("setmaxnreg.dec.sync.aligned.u32 80;");
    const int t = tid - 256, w = warp - 8;
    const float scale = 2.0f / (2048.0f * 512.0f);
    if (!helper) {
      {
        uint4 xv[8], gv[2];
#pragma unroll
        for (int i = 0; i < 4; i++) {
          const int r = 16 * j + 4 * w + i;
          const uint4* p = (const uint4*)(x + (size_t)(2 * rb + (r >> 6) + 32 * (r & 63)) * 512) + lane;
          xv[2 * i] = __ldg(p); xv[2 * i + 1] = __ldg(p + 32);
        }
        gv[0] = __ldg((const uint4*)gate_w + lane); gv[1] = __ldg((const uint4*)gate_w + lane + 32);
        if (w == 0) {
          const int c = lane >> 4, jj = 16 * idx + (lane & 15), jm = (2048 - jj) & 2047;
          const unsigned short* pr = (const unsigned short*)w_r + 256 * c;
          const unsigned short* pi = (const unsigned short*)w_i + 256 * c;
          const float wr = 0.5f * (bf_lo(__ldg(pr + jj * 257)) + bf_lo(__ldg(pr + jm * 257)));
          const float wi = 0.5f * (bf_lo(__ldg(pi + jj * 257)) - bf_lo(__ldg(pi + jm * 257)));
          g_Wh[c * 2048 + jj] = c ? make_float2(-wi, wr) : make_float2(wr, wi);
        }
        float z[4];
#pragma unroll
        for (int i = 0; i < 4; i++) {
          float a = 0.f;
#pragma unroll
          for (int hh = 0; hh < 2; hh++) {
            const uint4 u = xv[2 * i + hh], v = gv[hh];
            a = fmaf(bf_lo(u.x), bf_lo(v.x), a); a = fmaf(bf_hi(u.x), bf_hi(v.x), a);
            a = fmaf(bf_lo(u.y), bf_lo(v.y), a); a = fmaf(bf_hi(u.y), bf_hi(v.y), a);
            a = fmaf(bf_lo(u.z), bf_lo(v.z), a); a = fmaf(bf_hi(u.z), bf_hi(v.z), a);
            a = fmaf(bf_lo(u.w), bf_lo(v.w), a); a = fmaf(bf_hi(u.w), bf_hi(v.w), a);
          }
#pragma unroll
          for (int o = 16; o; o >>= 1) a += __shfl_xor_sync(0xffffffffu, a, o);
          z[i] = a;
        }
        if (lane < 4) {
          const float zz = lane == 0 ? z[0] : lane == 1 ? z[1] : lane == 2 ? z[2] : z[3];
          g_gate[rb * 128 + 16 * j + 4 * w + lane] = 1.0f / (1.0f + __expf(-zz));
        }
        asm volatile("bar.sync 1, 128;" ::: "memory");
        if (t == 0) { red_release(&g_cntG[32 * rb]); red_relaxed(&g_cntW[0]); PROF_EV(18); }
      }
      const int k = 16 * kg + (t & 15), j1 = 8 * tn + (t >> 4);
      {
        const unsigned short* p = (const unsigned short*)(smem + OFF_W) + (t >> 4) * 25 + (t & 15);
        uint32_t wv[32];
        if (t == 0) {
          mbar_wait(bars + 8 * (B_FULL + 7), 0);
          mbar_expect_tx(bars + 8 * B_W, 12288);
          tma4d(sb + OFF_W, &maps.wr, bars + 8 * B_W, 16 * kg, 0, tn, 0);
        }
        mbar_wait(bars + 8 * B_W, 0);
#pragma unroll
        for (int a = 0; a < 32; a++) wv[a] = p[a * 192];
        asm volatile("bar.sync 1, 128;" ::: "memory");
        if (t == 0) {
          mbar_expect_tx(bars + 8 * B_W, 12288);
          tma4d(sb + OFF_W, &maps.wi, bars + 8 * B_W, 16 * kg, 0, tn, 0);
        }
        mbar_wait(bars + 8 * B_W, 1);
#pragma unroll
        for (int a = 0; a < 32; a++) wv[a] |= (uint32_t)p[a * 192] << 16;
        asm volatile("bar.sync 1, 128;" ::: "memory");
#pragma unroll
        for (int a = 0; a < 8; a++) *(uint4*)(smem + OFF_W + (a * 128 + t) * 16) = make_uint4(wv[4 * a], wv[4 * a + 1], wv[4 * a + 2], wv[4 * a + 3]);
      }
      if (t == 0) PROF_EV(11);
      mbar_wait(bars + 8 * B_XR, 0);
      float2 v[32];
      const float2* src = g_X1p + (size_t)(kg * 8 + tn) * 4096 + t;
#pragma unroll
      for (int a = 0; a < 32; a++) v[a] = __ldcg(src + a * 128);
      dft<-1, 32, 0, 1>(v);
      float2 y[32];
#pragma unroll
      for (int a4 = 0; a4 < 8; a4++) {
        const uint4 ww = *(const uint4*)(smem + OFF_W + (a4 * 128 + t) * 16);
        const uint32_t wq[4] = {ww.x, ww.y, ww.z, ww.w};
#pragma unroll
        for (int e = 0; e < 4; e++) {
          const float2 z = v[brev(4 * a4 + e, 5)];
          const float wr = bf_lo(wq[e]), wi = bf_hi(wq[e]);
          y[4 * a4 + e] = make_float2(fmaf(z.x, wr, -z.y * wi), fmaf(z.x, wi, z.y * wr));
        }
      }
      dft<1, 32, 0, 1>(y);
      if (t == 0) PROF_EV(16);
      if (k != 0) {
        uint32_t* dst = g_Tp + j1 * 256 + k;
#pragma unroll
        for (int a = 0; a < 32; a++) dst[a * 64 * 256] = pack_bf16(y[brev(a, 5)].x * scale, y[brev(a, 5)].y * scale);
      }
      asm volatile("bar.sync 1, 128;" ::: "memory");
      if (t == 0) { PROF_EV(17); red_release(&g_cntT[32 * j]); PROF_EV(13); }
    } else if (w == 0) {
      const int c = lane >> 4, j1 = 16 * (blockIdx.x - 128) + (lane & 15);
      float2* wf = (float2*)smem;
      mbar_wait(bars + 8 * B_G, 0);
#pragma unroll
      for (int a = 0; a < 32; a++) wf[a * 32 + lane] = __ldcg(g_Wh + c * 2048 + j1 + 64 * a);
      if (t == 0) PROF_EV(11);
      mbar_wait(bars + 8 * B_XR, 0);
      float2 v[32];
#pragma unroll
      for (int a = 0; a < 32; a++) v[a] = __ldcg(g_X1s + (c * 32 + a) * 64 + j1);
      dft<-1, 32, 0, 1>(v);
      float2 y[32];
#pragma unroll
      for (int a = 0; a < 32; a++) {
        const float2 z = v[brev(a, 5)], wv = wf[a * 32 + lane];
        y[a] = make_float2(fmaf(z.x, wv.x, -z.y * wv.y), fmaf(z.x, wv.y, z.y * wv.x));
      }
      dft<1, 32, 0, 1>(y);
      if (t == 0) PROF_EV(16);
#pragma unroll
      for (int a = 0; a < 16; a++) {
        const float2 u0 = y[brev(2 * a, 5)], u1 = y[brev(2 * a + 1, 5)];
        const float2 keep = c ? u1 : u0, give = c ? u0 : u1;
        const float ox = __shfl_xor_sync(0xffffffffu, give.x, 16), oy = __shfl_xor_sync(0xffffffffu, give.y, 16);
        g_Tp[((2 * a + c) * 64 + j1) * 256] = pack_bf16((keep.x + ox) * (0.5f * scale), (keep.y + oy) * (0.5f * scale));
      }
      __syncwarp();
      if (t == 0) { PROF_EV(17); red_release(&g_cntT[0]); PROF_EV(13); }
    }
  } else {
    asm volatile("setmaxnreg.inc.sync.aligned.u32 200;");
    if (!helper) {
      const int wg = warp >> 2, w = warp & 3, g = lane >> 2, q = lane & 3;
      const bool elect = (tid & 127) == 0;
      uint32_t fph = 0;
      auto waitfull = [&](int s) { mbar_wait(bars + 8 * (B_FULL + s), (fph >> s) & 1); fph ^= 1u << s; };
      auto release = [&](int s) { if (elect) mbar_arrive(bars + 8 * (B_EMPTY + s)); };
      float c1[64], cA[64], c2[64], ci[64], ct[64];
      const int zero = blockIdx.x >> 16;
      uint32_t h[56], yf[16];
      const uint64_t dK = mkdesc(sb, 16, 1024, 1);
      const uint64_t dN = mkdesc(sb, 8192, 1024, 1);
      const uint64_t dM = mkdesc(sb, 4096, 512, 2);
      const uint32_t xo = wg * 512;
      int rs = 8, prev = 8;

      auto c1_step = [&](auto first, int kb) {
        waitfull(kb); waitfull(rs);
        wg_fence();
        const uint64_t dx = dK + (kb * 1024 + xo), df = dK + rs * 1024, dm = dM + (rs * 1024 + 512);
        mma_ss64<0, 0, decltype(first)::value>(c1, df, dx);
        mma_ss64<32, 1, decltype(first)::value>(c1, dx, dm);
#pragma unroll
        for (int k = 1; k < 4; k++) {
          mma_ss64<0, 0, 1>(c1, df + k * 2, dx + k * 2);
          mma_ss64<32, 1, 1>(c1, dx + k * 2, dm + k * 64);
        }
        wg_commit();
      };
      c1_step(I0(), 0);
      if (tid == 0) PROF_EV(1);
      rs = 9;
#pragma unroll 1
      for (int kb = 1; kb < 8; kb++) {
        c1_step(I1(), kb);
        wg_wait<1>();
        release(prev);
        prev = rs; if (++rs == 13) rs = 8;
      }
      auto ffn_step = [&](auto first, float (&acc)[64], int kb) {
        waitfull(rs);
        wg_fence();
        const uint64_t dx = dK + (kb * 1024 + xo), db = dN + rs * 1024;
        mma_ss128<0, 1, decltype(first)::value>(acc, dx, db, zero);
#pragma unroll
        for (int k = 1; k < 4; k++) mma_ss128<0, 1, 1>(acc, dx + k * 2, db + k * 128);
        wg_commit();
        wg_wait<1>();
      };
      ffn_step(I0(), c2, 0);
      release(prev); prev = rs; if (++rs == 13) rs = 8;
      fence_regs<0, 64>(c1);
      if (tid == 0) PROF_EV(2);
      mbar_wait(bars + 8 * B_G, 0);
      const float g0 = ((const float*)(smem + OFF_G))[wg * 64 + w * 16 + g], g1 = ((const float*)(smem + OFF_G))[wg * 64 + w * 16 + g + 8];
      const float o0 = 1.0f - g0, o1 = 1.0f - g1;
#pragma unroll
      for (int i = 0; i < 16; i++) yf[i] = pack_pin(c1[2 * i], c1[2 * i + 1]);
#pragma unroll
      for (int i = 0; i < 8; i++) {
        const float o = (i & 1) ? o1 : o0;
        h[48 + i] = pack_pin(fmaxf(c1[32 + 2 * i], 0.f) * c1[48 + 2 * i] * o, fmaxf(c1[33 + 2 * i], 0.f) * c1[49 + 2 * i] * o);
      }
      {
        const int e0 = rs, e1 = rs == 12 ? 8 : rs + 1;
        waitfull(e0); waitfull(e1);
        const int es = wg ? e1 : e0;
        wg_fence();
        mma_rs128<0, 1, 0>(cA, yf[0], yf[1], yf[2], yf[3], dN + es * 1024);
#pragma unroll
        for (int k = 1; k < 4; k++) mma_rs128<0, 1, 1>(cA, yf[4 * k], yf[4 * k + 1], yf[4 * k + 2], yf[4 * k + 3], dN + (es * 1024 + k * 128));
        wg_commit();
        wg_wait<1>();
        release(prev);
        rs = e1 == 12 ? 8 : e1 + 1;
        ffn_step(I1(), c2, 1);
        release(e0); release(e1);
        prev = rs; if (++rs == 13) rs = 8;
        fence_regs<0, 64>(cA);
        const int s0 = 2 * rb + wg;
        float2* dst = g_X1p + ((size_t)((2 * j + (w >> 1)) * 8) * 32 + s0) * 128 + (2 * q) * 16 + 8 * (w & 1) + g;
#pragma unroll
        for (int n = 0; n < 8; n++) {
#pragma unroll
          for (int e = 0; e < 2; e++)
            dst[n * 4096 + e * 16] = make_float2(cA[4 * n + e] - cA[34 + 4 * n + e], cA[32 + 4 * n + e] + cA[4 * n + 2 + e]);
        }
        if (j == 0 && w == 0 && g == 0) {
#pragma unroll
          for (int n = 0; n < 8; n++) {
#pragma unroll
            for (int e = 0; e < 2; e++) {
              g_X1s[s0 * 64 + 8 * n + 2 * q + e] = make_float2(cA[4 * n + e], cA[32 + 4 * n + e]);
              g_X1s[(32 + s0) * 64 + 8 * n + 2 * q + e] = make_float2(cA[4 * n + 2 + e], cA[34 + 4 * n + e]);
            }
          }
        }
        __syncwarp();
        if (lane == 0) mbar_arrive(bars + 8 * B_X1);
        if (tid == 0) PROF_EV(3);
      }
      auto glu = [&](float (&acc)[64], int ho) {
#pragma unroll
        for (int i = 0; i < 16; i++) {
          const float o = (i & 1) ? o1 : o0;
          h[ho + i] = pack_pin(fmaxf(acc[2 * i], 0.f) * acc[32 + 2 * i] * o, fmaxf(acc[2 * i + 1], 0.f) * acc[33 + 2 * i] * o);
        }
      };
#pragma unroll 1
      for (int kb = 2; kb < 8; kb++) { ffn_step(I1(), c2, kb); release(prev); prev = rs; if (++rs == 13) rs = 8; }
      ffn_step(I2(), cA, 0); release(prev); prev = rs; if (++rs == 13) rs = 8;
      fence_regs<0, 64>(c2);
      if (tid == 0) PROF_EV(4);
      glu(c2, 0);
#pragma unroll 1
      for (int kb = 1; kb < 8; kb++) { ffn_step(I1(), cA, kb); release(prev); prev = rs; if (++rs == 13) rs = 8; }
      ffn_step(I2(), c2, 0); release(prev); prev = rs; if (++rs == 13) rs = 8;
      fence_regs<0, 64>(cA);
      if (tid == 0) PROF_EV(5);
      glu(cA, 16);
#pragma unroll 1
      for (int kb = 1; kb < 8; kb++) { ffn_step(I1(), c2, kb); release(prev); release(kb - 1); prev = rs; if (++rs == 13) rs = 8; }
      int m = 2;
      bool round2 = false;
      auto piece = [&](auto off, int p, bool rel = true) {
        constexpr int O = decltype(off)::value;
        const int s = ringB(m);
        waitfull(s);
        wg_fence();
        const uint64_t db = dN + s * 1024;
        if (p == 0) {
          mma_rs64<O, 1, 0>(ct, h[0], h[1], h[2], h[3], db);
#pragma unroll
          for (int k = 1; k < 6; k++) mma_rs64<O, 1, 1>(ct, h[4 * k], h[4 * k + 1], h[4 * k + 2], h[4 * k + 3], db + k * 128);
        } else if (p == 1) {
#pragma unroll
          for (int k = 0; k < 6; k++) mma_rs64<O, 1, 1>(ct, h[24 + 4 * k], h[25 + 4 * k], h[26 + 4 * k], h[27 + 4 * k], db + k * 128);
        } else {
#pragma unroll
          for (int k = 0; k < 4; k++) mma_rs64<O, 1, 1>(ct, yf[4 * k], yf[4 * k + 1], yf[4 * k + 2], yf[4 * k + 3], db + k * 128);
#pragma unroll
          for (int k = 0; k < 2; k++) mma_rs64<O, 1, 1>(ct, h[48 + 4 * k], h[49 + 4 * k], h[50 + 4 * k], h[51 + 4 * k], db + (4 + k) * 128);
        }
        wg_commit();
        wg_wait<1>();
        if (rel) release(prev);
        prev = round2 ? (B_FIN - B_EMPTY) + m : s;
        if (++m == 13) { m = 0; round2 = true; }
      };
      auto send = [&](auto off, int t) {
        constexpr int O = decltype(off)::value;
        fence_regs<O, 32>(ct);
        uint4* dst = g_part + (size_t)((rb * 8 + ((j + 1 + t) & 7)) * 8 + t) * 1024 + tid;
#pragma unroll
        for (int i = 0; i < 4; i++)
          dst[i * 256] = make_uint4(pack_bf16(ct[O + 8 * i], ct[O + 8 * i + 1]), pack_bf16(ct[O + 8 * i + 2], ct[O + 8 * i + 3]),
                                    pack_bf16(ct[O + 8 * i + 4], ct[O + 8 * i + 5]), pack_bf16(ct[O + 8 * i + 6], ct[O + 8 * i + 7]));
        __syncwarp();
        if (lane == 0) mbar_arrive(bars + 8 * (B_P + t));
      };
      wg_wait<0>();
      release(prev); release(7);
      fence_regs<0, 64>(c2);
      glu(c2, 32);
      waitfull(0); waitfull(1);
      if (tid == 0) PROF_EV(6);
      mbar_wait(bars + 8 * B_T, 0);
      if (tid == 0) PROF_EV(7);
      wg_fence();
      {
        const uint64_t dt = dN + ((OFF_W >> 4) + xo), de = dK + wg * 1024;
        mma_ss64<0, 1, 0>(ci, de, dt);
        mma_ss64<32, 1, 0>(ci, de + 512, dt);
#pragma unroll
        for (int k = 1; k < 4; k++) {
          mma_ss64<0, 1, 1>(ci, de + k * 2, dt + k * 128);
          mma_ss64<32, 1, 1>(ci, de + (512 + k * 2), dt + k * 128);
        }
      }
      wg_commit();
      piece(I0(), 0, false);
      release(0); release(1);
      fence_regs<0, 64>(ci);
#pragma unroll
      for (int i = 0; i < 16; i++) {
        const float gg = (i & 1) ? g1 : g0;
        yf[i] = pack_pin((ci[2 * i] + ci[33 + 2 * i]) * gg, (ci[2 * i + 1] - ci[32 + 2 * i]) * gg);
      }
      piece(I0(), 1); piece(I0(), 2);
      if (tid == 0) PROF_EV(8);
#pragma unroll 1
      for (int t = 1; t < 7; t += 2) {
        piece(I32(), 0); send(I0(), t - 1); piece(I32(), 1); piece(I32(), 2);
        piece(I0(), 0); send(I32(), t); piece(I0(), 1); piece(I0(), 2);
      }
      piece(I32(), 0); send(I0(), 6); piece(I32(), 1); piece(I32(), 2);
      if (tid == 0) PROF_EV(9);
      {
        float sum[32];
#pragma unroll
        for (int t = 0; t < 7; t++) {
          mbar_wait(bars + 8 * (B_R + t), 0);
          if (t == 6) { if (tid == 0) PROF_EV(14); }
          const uint4* src = (const uint4*)(smem + ringB(t) * SLOT) + tid;
#pragma unroll
          for (int i = 0; i < 4; i++) {
            const uint4 p = src[i * 256];
            const uint32_t u[4] = {p.x, p.y, p.z, p.w};
#pragma unroll
            for (int e = 0; e < 4; e++) {
              if (t == 0) { sum[8 * i + 2 * e] = bf_lo(u[e]); sum[8 * i + 2 * e + 1] = bf_hi(u[e]); }
              else { sum[8 * i + 2 * e] += bf_lo(u[e]); sum[8 * i + 2 * e + 1] += bf_hi(u[e]); }
            }
          }
          if (t == 5) {
            wg_wait<0>();
            fence_regs<32, 32>(ct);
#pragma unroll
            for (int i = 0; i < 32; i++) sum[i] += ct[32 + i];
          }
        }
        const uint32_t stg = sb + OFF_W + warp * 2048;
        const int mr = (lane & 7) + ((lane >> 3) & 1) * 8, mc = lane >> 4;
#pragma unroll
        for (int i = 0; i < 4; i++) {
          const uint32_t a = stg + mr * 128 + (((2 * i + mc) ^ (mr & 7)) << 4);
          asm volatile("stmatrix.sync.aligned.m8n8.x4.shared.b16 [%0], {%1,%2,%3,%4};" ::"r"(a), "r"(pack_bf16(sum[8 * i], sum[8 * i + 1])),
                       "r"(pack_bf16(sum[8 * i + 2], sum[8 * i + 3])), "r"(pack_bf16(sum[8 * i + 4], sum[8 * i + 5])),
                       "r"(pack_bf16(sum[8 * i + 6], sum[8 * i + 7])) : "memory");
        }
        __syncwarp();
#pragma unroll
        for (int i = 0; i < 4; i++) {
          const int r = 4 * i + (lane >> 3), c = lane & 7;
          const uint4 v = *(const uint4*)(smem + OFF_W + warp * 2048 + r * 128 + ((c ^ (r & 7)) << 4));
          *(uint4*)(out + (size_t)(2 * rb + wg + 32 * (16 * w + r)) * 512 + 64 * j + 8 * c) = v;
        }
      }
      if (tid == 0) { PROF_EV(15); PROF_CK(41); }
    }
  }
}

typedef CUresult (*EncodeFn)(CUtensorMap*, CUtensorMapDataType, cuuint32_t, void*, const cuuint64_t*, const cuuint64_t*, const cuuint32_t*,
                             const cuuint32_t*, CUtensorMapInterleave, CUtensorMapSwizzle, CUtensorMapL2promotion, CUtensorMapFloatOOBfill);

static void encode(EncodeFn f, CUtensorMap* m, const void* base, int rank, const cuuint64_t* dims, const cuuint64_t* strides, const cuuint32_t* box,
                   CUtensorMapSwizzle sw) {
  cuuint32_t es[5] = {1, 1, 1, 1, 1};
  f(m, CU_TENSOR_MAP_DATA_TYPE_BFLOAT16, rank, (void*)base, dims, strides, box, es, CU_TENSOR_MAP_INTERLEAVE_NONE, sw,
    CU_TENSOR_MAP_L2_PROMOTION_L2_128B, CU_TENSOR_MAP_FLOAT_OOB_FILL_NONE);
}

extern "C" void kernel_launch(void* const* d_in, const int* in_sizes, int n_in, void* d_out, int out_size) {
  (void)in_sizes; (void)n_in; (void)out_size;
  const __nv_bfloat16* x = (const __nv_bfloat16*)d_in[0];
  const __nv_bfloat16* w_r = (const __nv_bfloat16*)d_in[1];
  const __nv_bfloat16* w_i = (const __nv_bfloat16*)d_in[2];
  const __nv_bfloat16* Wg = (const __nv_bfloat16*)d_in[4];
  const __nv_bfloat16* Wu = (const __nv_bfloat16*)d_in[5];
  const __nv_bfloat16* Wd = (const __nv_bfloat16*)d_in[6];
  const __nv_bfloat16* gw = (const __nv_bfloat16*)d_in[7];

  void* fp = nullptr; cudaDriverEntryPointQueryResult qr;
  cudaGetDriverEntryPoint("cuTensorMapEncodeTiled", &fp, cudaEnableDefault, &qr);
  EncodeFn enc = (EncodeFn)fp;
  void *pFT, *pET, *pT;
  cudaGetSymbolAddress(&pFT, g_FT); cudaGetSymbolAddress(&pET, g_ET); cudaGetSymbolAddress(&pT, g_Tp);

  Maps mp;
  const CUtensorMapSwizzle S128 = CU_TENSOR_MAP_SWIZZLE_128B, S64 = CU_TENSOR_MAP_SWIZZLE_64B;
  { cuuint64_t d[3] = {512, 64, 32}, s[2] = {32768, 1024}; cuuint32_t b[3] = {64, 64, 2}; encode(enc, &mp.x, x, 3, d, s, b, S128); }
  { cuuint64_t d[2] = {512, 512}, s[1] = {1024}; cuuint32_t b[2] = {64, 64}; encode(enc, &mp.ft, pFT, 2, d, s, b, S128); }
  { cuuint64_t d[4] = {512, 2, 8, 32}, s[3] = {8192, 1024, 16384}; cuuint32_t b[4] = {64, 2, 8, 4}; encode(enc, &mp.fg, pFT, 4, d, s, b, S128); }
  { cuuint64_t d[4] = {64, 64, 2, 32}, s[3] = {8192, 128, 256}; cuuint32_t b[4] = {64, 64, 2, 1}; encode(enc, &mp.e, pET, 4, d, s, b, S128); }
  { cuuint64_t d[2] = {1792, 512}, s[1] = {3584}; cuuint32_t b[2] = {64, 64}, b2[2] = {32, 64};
    encode(enc, &mp.g64, Wg, 2, d, s, b, S128); encode(enc, &mp.u64, Wu, 2, d, s, b, S128);
    encode(enc, &mp.g32, Wg, 2, d, s, b2, S64); encode(enc, &mp.u32, Wu, 2, d, s, b2, S64); }
  { cuuint64_t d[2] = {512, 1792}, s[1] = {1024}; cuuint32_t b[2] = {64, 96}, b2[2] = {64, 32};
    encode(enc, &mp.d96, Wd, 2, d, s, b, S128); encode(enc, &mp.d32, Wd, 2, d, s, b2, S128); }
  { cuuint64_t d[3] = {512, 64, 32}, s[2] = {1024, 65536}; cuuint32_t b[3] = {64, 64, 2}; encode(enc, &mp.t, pT, 3, d, s, b, S128); }

  { cuuint64_t d[4] = {264, 8, 8, 32}, s[3] = {512, 4112, 32896}; cuuint32_t b[4] = {24, 8, 1, 32};
    encode(enc, &mp.wr, w_r, 4, d, s, b, CU_TENSOR_MAP_SWIZZLE_NONE); encode(enc, &mp.wi, w_i, 4, d, s, b, CU_TENSOR_MAP_SWIZZLE_NONE); }

  cudaFuncSetAttribute(fused_kernel, cudaFuncAttributeMaxDynamicSharedMemorySize, SMEM_BYTES);
  fused_kernel<<<NCTA, 512, SMEM_BYTES>>>(mp, x, w_r, w_i, gw, (__nv_bfloat16*)d_out);
}
```

```cpp
#include <cuda_runtime.h>
#include <cuda_bf16.h>
#include <cuda.h>
#include <stdint.h>

namespace tbl {
constexpr double PI = 3.14159265358979323846264338327950288;
constexpr double sin_s(double x) { double t = x, s = x; for (int n = 1; n < 12; n++) { t *= -x * x / ((2 * n) * (2 * n + 1)); s += t; } return s; }
constexpr double cos_s(double x) { double t = 1, s = 1; for (int n = 1; n < 12; n++) { t *= -x * x / ((2 * n - 1) * (2 * n)); s += t; } return s; }
constexpr double cos2048(int m) {
  m &= 2047; if (m > 1024) m = 2048 - m;
  bool neg = false; if (m > 512) { m = 1024 - m; neg = true; }
  double v = (m <= 256) ? cos_s(2 * PI * m / 2048) : sin_s(2 * PI * (512 - m) / 2048);
  return neg ? -v : v;
}
constexpr uint16_t to_bf16(double v) {
  if (v == 0) return 0;
  uint16_t s = 0; if (v < 0) { s = 0x8000; v = -v; }
  int e = 0; while (v >= 2) { v /= 2; e++; } while (v < 1) { v *= 2; e--; }
  double m = (v - 1) * 128; int mi = (int)m; double fr = m - mi;
  if (fr > 0.5 || (fr == 0.5 && (mi & 1))) mi++;
  if (mi == 128) { mi = 0; e++; }
  return (uint16_t)(s | ((e + 127) << 7) | mi);
}
struct CosT { uint16_t v[2048]; constexpr CosT() : v() { for (int i = 0; i < 2048; i++) v[i] = to_bf16(cos2048(i)); } };
struct alignas(1024) FT {
  uint16_t v[512 * 512];
  constexpr FT() : v() {
    CosT c;
    for (int r = 0; r < 512; r++) {
      int k = (r >> 4) * 8 + (r & 7), e = (r >> 3) & 1;
      int mul = 4 * k, add = e ? 512 : 0;
      if (k == 0 && e == 1) { mul = 1024; add = 0; }
      for (int d = 0; d < 512; d++) v[r * 512 + d] = c.v[(d * mul + add) & 2047];
    }
  }
};
struct alignas(1024) ET {
  uint16_t v[2048 * 128];
  constexpr ET() : v() {
    CosT c;
    for (int s = 0; s < 2048; s++)
      for (int j = 0; j < 64; j++) { v[s * 128 + j] = c.v[(s * j) & 2047]; v[s * 128 + 64 + j] = c.v[(s * j + 512) & 2047]; }
  }
};
template <int A> struct W32 {
  static constexpr float c = (float)cos2048(A * 64);
  static constexpr float s = (float)cos2048(A * 64 - 512);
};
}

__device__ constexpr tbl::FT g_FT = tbl::FT();
__device__ constexpr tbl::ET g_ET = tbl::ET();

__device__ __align__(1024) float2 g_X1p[128 * 32 * 128];
__device__ __align__(1024) float2 g_X1s[2 * 32 * 64];
__device__ __align__(1024) float2 g_T[32 * 64 * 256];
__device__ __align__(1024) uint4 g_part[128 * 3 * 1024];
__device__ __align__(16) float g_gate[16 * 128];
__device__ __align__(16) float2 g_Wh[2 * 2048];
__device__ unsigned g_epoch[132 * 8];
#define PROF_EV(i) do {} while (0)
#define PROF_CK(i) do {} while (0)

__device__ __forceinline__ uint32_t smem_u32(const void* p) { return (uint32_t)__cvta_generic_to_shared(p); }
__device__ __forceinline__ void mbar_init(uint32_t bar, uint32_t cnt) { asm volatile("mbarrier.init.shared::cta.b64 [%0], %1;" ::"r"(bar), "r"(cnt)); }
__device__ __forceinline__ void mbar_expect_tx(uint32_t bar, uint32_t bytes) { asm volatile("mbarrier.arrive.expect_tx.shared::cta.b64 _, [%0], %1;" ::"r"(bar), "r"(bytes) : "memory"); }
__device__ __forceinline__ void mbar_arrive(uint32_t bar) { asm volatile("mbarrier.arrive.shared::cta.b64 _, [%0];" ::"r"(bar) : "memory"); }
__device__ __forceinline__ bool mbar_try(uint32_t bar, uint32_t parity) {
  uint32_t ok;
  asm volatile("{\n.reg .pred p;\nmbarrier.try_wait.parity.shared::cta.b64 p, [%1], %2;\nselp.u32 %0, 1, 0, p;\n}" : "=r"(ok) : "r"(bar), "r"(parity) : "memory");
  return ok;
}
__device__ __forceinline__ void mbar_wait(uint32_t bar, uint32_t parity) {
  if (mbar_try(bar, parity)) return;
  const uint32_t t0 = (uint32_t)clock();
  while (!mbar_try(bar, parity)) { if ((uint32_t)clock() - t0 > (1u << 30)) __trap(); }
}
__device__ __forceinline__ void spin_guard(uint32_t t0) { if ((uint32_t)clock() - t0 > (1u << 30)) __trap(); }
__device__ __forceinline__ float tagf(float v, uint32_t tag) { return __uint_as_float((__float_as_uint(v) & ~1u) | tag); }
__device__ __forceinline__ float untag(float v) { return __uint_as_float(__float_as_uint(v) & ~1u); }
__device__ __forceinline__ void st_x2(float2* p, float a, float b) { asm volatile("st.relaxed.gpu.global.v2.f32 [%0], {%1,%2};" ::"l"(p), "f"(a), "f"(b) : "memory"); }
__device__ __forceinline__ float2 ld_x2(const float2* p) { float2 v; asm volatile("ld.relaxed.gpu.global.v2.f32 {%0,%1}, [%2];" : "=f"(v.x), "=f"(v.y) : "l"(p) : "memory"); return v; }
__device__ __forceinline__ uint32_t ld_x1(const void* p) { uint32_t v; asm volatile("ld.relaxed.gpu.global.u32 %0, [%1];" : "=r"(v) : "l"(p) : "memory"); return v; }
__device__ __forceinline__ uint4 ld_x4(const void* p) { uint4 v; asm volatile("ld.relaxed.gpu.global.v4.u32 {%0,%1,%2,%3}, [%4];" : "=r"(v.x), "=r"(v.y), "=r"(v.z), "=r"(v.w) : "l"(p) : "memory"); return v; }
__device__ __forceinline__ void st_x4(void* p, uint32_t a, uint32_t b, uint32_t c, uint32_t d) { asm volatile("st.relaxed.gpu.global.v4.u32 [%0], {%1,%2,%3,%4};" ::"l"(p), "r"(a), "r"(b), "r"(c), "r"(d) : "memory"); }
__device__ __forceinline__ uint32_t mapa(uint32_t a, uint32_t cta) { uint32_t r; asm volatile("mapa.shared::cluster.u32 %0, %1, %2;" : "=r"(r) : "r"(a), "r"(cta)); return r; }
__device__ __forceinline__ void probe_tag(const void* p, uint32_t tag) {
  const uint32_t t0 = (uint32_t)clock();
  while (__any_sync(0xffffffffu, (ld_x1(p) ^ tag) & 1)) { __nanosleep(64); spin_guard(t0); }
}
__device__ __forceinline__ void load32_tagged(float2 (&v)[32], const float2* src, int stride, uint32_t tag) {
  const uint32_t t0 = (uint32_t)clock();
  for (;;) {
    uint32_t bad = 0;
#pragma unroll
    for (int a = 0; a < 32; a++) v[a] = ld_x2(src + a * stride);
#pragma unroll
    for (int a = 0; a < 32; a++) bad |= __float_as_uint(v[a].x) ^ tag;
    if (!__any_sync(0xffffffffu, bad & 1)) break;
    spin_guard(t0);
  }
#pragma unroll
  for (int a = 0; a < 32; a++) v[a].x = untag(v[a].x);
}
__device__ __forceinline__ void tma2d(uint32_t dst, const CUtensorMap* m, uint32_t bar, int c0, int c1) {
  asm volatile("cp.async.bulk.tensor.2d.shared::cluster.global.mbarrier::complete_tx::bytes [%0], [%1, {%3, %4}], [%2];" ::"r"(dst), "l"(m), "r"(bar), "r"(c0), "r"(c1) : "memory");
}
__device__ __forceinline__ void tma3d(uint32_t dst, const CUtensorMap* m, uint32_t bar, int c0, int c1, int c2) {
  asm volatile("cp.async.bulk.tensor.3d.shared::cluster.global.mbarrier::complete_tx::bytes [%0], [%1, {%3, %4, %5}], [%2];" ::"r"(dst), "l"(m), "r"(bar), "r"(c0), "r"(c1), "r"(c2) : "memory");
}
__device__ __forceinline__ void tma4d(uint32_t dst, const CUtensorMap* m, uint32_t bar, int c0, int c1, int c2, int c3) {
  asm volatile("cp.async.bulk.tensor.4d.shared::cluster.global.mbarrier::complete_tx::bytes [%0], [%1, {%3, %4, %5, %6}], [%2];" ::"r"(dst), "l"(m), "r"(bar), "r"(c0), "r"(c1), "r"(c2), "r"(c3) : "memory");
}
__device__ __forceinline__ void wg_fence() { asm volatile("wgmma.fence.sync.aligned;" ::: "memory"); }
__device__ __forceinline__ void wg_commit() { asm volatile("wgmma.commit_group.sync.aligned;" ::: "memory"); }
template <int N> __device__ __forceinline__ void wg_wait() { asm volatile("wgmma.wait_group.sync.aligned %0;" ::"n"(N) : "memory"); }
template <int O, int N, int NN> __device__ __forceinline__ void fence_regs(float (&d)[NN]) {
#pragma unroll
  for (int i = 0; i < N; i++) asm volatile("" : "+f"(d[O + i])::"memory");
}
__device__ __forceinline__ uint32_t pack_bf16(float lo, float hi) {
  uint32_t r; asm("cvt.rn.bf16x2.f32 %0, %1, %2;" : "=r"(r) : "f"(hi), "f"(lo)); return r;
}
__device__ __forceinline__ uint32_t pack_pin(float lo, float hi) {
  uint32_t r; asm volatile("cvt.rn.bf16x2.f32 %0, %1, %2;" : "=r"(r) : "f"(hi), "f"(lo) : "memory"); return r;
}
__device__ __forceinline__ float bf_lo(uint32_t u) { return __uint_as_float(u << 16); }
__device__ __forceinline__ float bf_hi(uint32_t u) { return __uint_as_float(u & 0xffff0000u); }

constexpr uint32_t H128 = 0x40000040u;
constexpr uint32_t H64 = 0x80000020u;
template<int O,int TB,int ACC,uint32_t HB = H128,int NN> __device__ __forceinline__ void mma_ss64(float (&d)[NN], uint32_t da, uint32_t db, int sd = 0){
  if constexpr (ACC == 1) asm volatile("{\n.reg .b64 da, db;\nmov.b64 da, {%32, %36};\nmov.b64 db, {%33, %35};\nwgmma.mma_async.sync.aligned.m64n64k16.f32.bf16.bf16 {%0,%1,%2,%3,%4,%5,%6,%7,%8,%9,%10,%11,%12,%13,%14,%15,%16,%17,%18,%19,%20,%21,%22,%23,%24,%25,%26,%27,%28,%29,%30,%31}, da, db, 1, 1, 1, 0, %34;\n}"
   : "+f"(d[O+0]), "+f"(d[O+1]), "+f"(d[O+2]), "+f"(d[O+3]), "+f"(d[O+4]), "+f"(d[O+5]), "+f"(d[O+6]), "+f"(d[O+7]), "+f"(d[O+8]), "+f"(d[O+9]), "+f"(d[O+10]), "+f"(d[O+11]), "+f"(d[O+12]), "+f"(d[O+13]), "+f"(d[O+14]), "+f"(d[O+15]), "+f"(d[O+16]), "+f"(d[O+17]), "+f"(d[O+18]), "+f"(d[O+19]), "+f"(d[O+20]), "+f"(d[O+21]), "+f"(d[O+22]), "+f"(d[O+23]), "+f"(d[O+24]), "+f"(d[O+25]), "+f"(d[O+26]), "+f"(d[O+27]), "+f"(d[O+28]), "+f"(d[O+29]), "+f"(d[O+30]), "+f"(d[O+31])
   : "r"(da), "r"(db), "n"(TB), "n"(HB), "n"(H128));
  else if constexpr (ACC == 0) asm volatile("{\n.reg .b64 da, db;\nmov.b64 da, {%32, %36};\nmov.b64 db, {%33, %35};\nwgmma.mma_async.sync.aligned.m64n64k16.f32.bf16.bf16 {%0,%1,%2,%3,%4,%5,%6,%7,%8,%9,%10,%11,%12,%13,%14,%15,%16,%17,%18,%19,%20,%21,%22,%23,%24,%25,%26,%27,%28,%29,%30,%31}, da, db, 0, 1, 1, 0, %34;\n}"
   : "=f"(d[O+0]), "=f"(d[O+1]), "=f"(d[O+2]), "=f"(d[O+3]), "=f"(d[O+4]), "=f"(d[O+5]), "=f"(d[O+6]), "=f"(d[O+7]), "=f"(d[O+8]), "=f"(d[O+9]), "=f"(d[O+10]), "=f"(d[O+11]), "=f"(d[O+12]), "=f"(d[O+13]), "=f"(d[O+14]), "=f"(d[O+15]), "=f"(d[O+16]), "=f"(d[O+17]), "=f"(d[O+18]), "=f"(d[O+19]), "=f"(d[O+20]), "=f"(d[O+21]), "=f"(d[O+22]), "=f"(d[O+23]), "=f"(d[O+24]), "=f"(d[O+25]), "=f"(d[O+26]), "=f"(d[O+27]), "=f"(d[O+28]), "=f"(d[O+29]), "=f"(d[O+30]), "=f"(d[O+31])
   : "r"(da), "r"(db), "n"(TB), "n"(HB), "n"(H128));
  else asm volatile("{\n.reg .pred p;\n.reg .b64 da, db;\nmov.b64 da, {%32, %36};\nmov.b64 db, {%33, %35};\nsetp.ne.b32 p, %37, 0;\nwgmma.mma_async.sync.aligned.m64n64k16.f32.bf16.bf16 {%0,%1,%2,%3,%4,%5,%6,%7,%8,%9,%10,%11,%12,%13,%14,%15,%16,%17,%18,%19,%20,%21,%22,%23,%24,%25,%26,%27,%28,%29,%30,%31}, da, db, p, 1, 1, 0, %34;\n}"
   : "+f"(d[O+0]), "+f"(d[O+1]), "+f"(d[O+2]), "+f"(d[O+3]), "+f"(d[O+4]), "+f"(d[O+5]), "+f"(d[O+6]), "+f"(d[O+7]), "+f"(d[O+8]), "+f"(d[O+9]), "+f"(d[O+10]), "+f"(d[O+11]), "+f"(d[O+12]), "+f"(d[O+13]), "+f"(d[O+14]), "+f"(d[O+15]), "+f"(d[O+16]), "+f"(d[O+17]), "+f"(d[O+18]), "+f"(d[O+19]), "+f"(d[O+20]), "+f"(d[O+21]), "+f"(d[O+22]), "+f"(d[O+23]), "+f"(d[O+24]), "+f"(d[O+25]), "+f"(d[O+26]), "+f"(d[O+27]), "+f"(d[O+28]), "+f"(d[O+29]), "+f"(d[O+30]), "+f"(d[O+31])
   : "r"(da), "r"(db), "n"(TB), "n"(HB), "n"(H128), "r"(sd));
}
template<int O,int TB,int ACC,uint32_t HB = H128,int NN> __device__ __forceinline__ void mma_rs64(float (&d)[NN], uint32_t a0, uint32_t a1, uint32_t a2, uint32_t a3, uint32_t db, int sd = 0){
  if constexpr (ACC == 1) asm volatile("{\n.reg .b64 db;\nmov.b64 db, {%36, %38};\nwgmma.mma_async.sync.aligned.m64n64k16.f32.bf16.bf16 {%0,%1,%2,%3,%4,%5,%6,%7,%8,%9,%10,%11,%12,%13,%14,%15,%16,%17,%18,%19,%20,%21,%22,%23,%24,%25,%26,%27,%28,%29,%30,%31}, {%32,%33,%34,%35}, db, 1, 1, 1, %37;\n}"
   : "+f"(d[O+0]), "+f"(d[O+1]), "+f"(d[O+2]), "+f"(d[O+3]), "+f"(d[O+4]), "+f"(d[O+5]), "+f"(d[O+6]), "+f"(d[O+7]), "+f"(d[O+8]), "+f"(d[O+9]), "+f"(d[O+10]), "+f"(d[O+11]), "+f"(d[O+12]), "+f"(d[O+13]), "+f"(d[O+14]), "+f"(d[O+15]), "+f"(d[O+16]), "+f"(d[O+17]), "+f"(d[O+18]), "+f"(d[O+19]), "+f"(d[O+20]), "+f"(d[O+21]), "+f"(d[O+22]), "+f"(d[O+23]), "+f"(d[O+24]), "+f"(d[O+25]), "+f"(d[O+26]), "+f"(d[O+27]), "+f"(d[O+28]), "+f"(d[O+29]), "+f"(d[O+30]), "+f"(d[O+31])
   : "r"(a0), "r"(a1), "r"(a2), "r"(a3), "r"(db), "n"(TB), "n"(HB));
  else if constexpr (ACC == 0) asm volatile("{\n.reg .b64 db;\nmov.b64 db, {%36, %38};\nwgmma.mma_async.sync.aligned.m64n64k16.f32.bf16.bf16 {%0,%1,%2,%3,%4,%5,%6,%7,%8,%9,%10,%11,%12,%13,%14,%15,%16,%17,%18,%19,%20,%21,%22,%23,%24,%25,%26,%27,%28,%29,%30,%31}, {%32,%33,%34,%35}, db, 0, 1, 1, %37;\n}"
   : "=f"(d[O+0]), "=f"(d[O+1]), "=f"(d[O+2]), "=f"(d[O+3]), "=f"(d[O+4]), "=f"(d[O+5]), "=f"(d[O+6]), "=f"(d[O+7]), "=f"(d[O+8]), "=f"(d[O+9]), "=f"(d[O+10]), "=f"(d[O+11]), "=f"(d[O+12]), "=f"(d[O+13]), "=f"(d[O+14]), "=f"(d[O+15]), "=f"(d[O+16]), "=f"(d[O+17]), "=f"(d[O+18]), "=f"(d[O+19]), "=f"(d[O+20]), "=f"(d[O+21]), "=f"(d[O+22]), "=f"(d[O+23]), "=f"(d[O+24]), "=f"(d[O+25]), "=f"(d[O+26]), "=f"(d[O+27]), "=f"(d[O+28]), "=f"(d[O+29]), "=f"(d[O+30]), "=f"(d[O+31])
   : "r"(a0), "r"(a1), "r"(a2), "r"(a3), "r"(db), "n"(TB), "n"(HB));
  else asm volatile("{\n.reg .pred p;\n.reg .b64 db;\nmov.b64 db, {%36, %38};\nsetp.ne.b32 p, %39, 0;\nwgmma.mma_async.sync.aligned.m64n64k16.f32.bf16.bf16 {%0,%1,%2,%3,%4,%5,%6,%7,%8,%9,%10,%11,%12,%13,%14,%15,%16,%17,%18,%19,%20,%21,%22,%23,%24,%25,%26,%27,%28,%29,%30,%31}, {%32,%33,%34,%35}, db, p, 1, 1, %37;\n}"
   : "+f"(d[O+0]), "+f"(d[O+1]), "+f"(d[O+2]), "+f"(d[O+3]), "+f"(d[O+4]), "+f"(d[O+5]), "+f"(d[O+6]), "+f"(d[O+7]), "+f"(d[O+8]), "+f"(d[O+9]), "+f"(d[O+10]), "+f"(d[O+11]), "+f"(d[O+12]), "+f"(d[O+13]), "+f"(d[O+14]), "+f"(d[O+15]), "+f"(d[O+16]), "+f"(d[O+17]), "+f"(d[O+18]), "+f"(d[O+19]), "+f"(d[O+20]), "+f"(d[O+21]), "+f"(d[O+22]), "+f"(d[O+23]), "+f"(d[O+24]), "+f"(d[O+25]), "+f"(d[O+26]), "+f"(d[O+27]), "+f"(d[O+28]), "+f"(d[O+29]), "+f"(d[O+30]), "+f"(d[O+31])
   : "r"(a0), "r"(a1), "r"(a2), "r"(a3), "r"(db), "n"(TB), "n"(HB), "r"(sd));
}
template<int O,int TB,int ACC,uint32_t HB = H128,int NN> __device__ __forceinline__ void mma_ss128(float (&d)[NN], uint32_t da, uint32_t db, int sd = 0){
  if constexpr (ACC == 1) asm volatile("{\n.reg .b64 da, db;\nmov.b64 da, {%64, %68};\nmov.b64 db, {%65, %67};\nwgmma.mma_async.sync.aligned.m64n128k16.f32.bf16.bf16 {%0,%1,%2,%3,%4,%5,%6,%7,%8,%9,%10,%11,%12,%13,%14,%15,%16,%17,%18,%19,%20,%21,%22,%23,%24,%25,%26,%27,%28,%29,%30,%31,%32,%33,%34,%35,%36,%37,%38,%39,%40,%41,%42,%43,%44,%45,%46,%47,%48,%49,%50,%51,%52,%53,%54,%55,%56,%57,%58,%59,%60,%61,%62,%63}, da, db, 1, 1, 1, 0, %66;\n}"
   : "+f"(d[O+0]), "+f"(d[O+1]), "+f"(d[O+2]), "+f"(d[O+3]), "+f"(d[O+4]), "+f"(d[O+5]), "+f"(d[O+6]), "+f"(d[O+7]), "+f"(d[O+8]), "+f"(d[O+9]), "+f"(d[O+10]), "+f"(d[O+11]), "+f"(d[O+12]), "+f"(d[O+13]), "+f"(d[O+14]), "+f"(d[O+15]), "+f"(d[O+16]), "+f"(d[O+17]), "+f"(d[O+18]), "+f"(d[O+19]), "+f"(d[O+20]), "+f"(d[O+21]), "+f"(d[O+22]), "+f"(d[O+23]), "+f"(d[O+24]), "+f"(d[O+25]), "+f"(d[O+26]), "+f"(d[O+27]), "+f"(d[O+28]), "+f"(d[O+29]), "+f"(d[O+30]), "+f"(d[O+31]), "+f"(d[O+32]), "+f"(d[O+33]), "+f"(d[O+34]), "+f"(d[O+35]), "+f"(d[O+36]), "+f"(d[O+37]), "+f"(d[O+38]), "+f"(d[O+39]), "+f"(d[O+40]), "+f"(d[O+41]), "+f"(d[O+42]), "+f"(d[O+43]), "+f"(d[O+44]), "+f"(d[O+45]), "+f"(d[O+46]), "+f"(d[O+47]), "+f"(d[O+48]), "+f"(d[O+49]), "+f"(d[O+50]), "+f"(d[O+51]), "+f"(d[O+52]), "+f"(d[O+53]), "+f"(d[O+54]), "+f"(d[O+55]), "+f"(d[O+56]), "+f"(d[O+57]), "+f"(d[O+58]), "+f"(d[O+59]), "+f"(d[O+60]), "+f"(d[O+61]), "+f"(d[O+62]), "+f"(d[O+63])
   : "r"(da), "r"(db), "n"(TB), "n"(HB), "n"(H128));
  else if constexpr (ACC == 0) asm volatile("{\n.reg .b64 da, db;\nmov.b64 da, {%64, %68};\nmov.b64 db, {%65, %67};\nwgmma.mma_async.sync.aligned.m64n128k16.f32.bf16.bf16 {%0,%1,%2,%3,%4,%5,%6,%7,%8,%9,%10,%11,%12,%13,%14,%15,%16,%17,%18,%19,%20,%21,%22,%23,%24,%25,%26,%27,%28,%29,%30,%31,%32,%33,%34,%35,%36,%37,%38,%39,%40,%41,%42,%43,%44,%45,%46,%47,%48,%49,%50,%51,%52,%53,%54,%55,%56,%57,%58,%59,%60,%61,%62,%63}, da, db, 0, 1, 1, 0, %66;\n}"
   : "=f"(d[O+0]), "=f"(d[O+1]), "=f"(d[O+2]), "=f"(d[O+3]), "=f"(d[O+4]), "=f"(d[O+5]), "=f"(d[O+6]), "=f"(d[O+7]), "=f"(d[O+8]), "=f"(d[O+9]), "=f"(d[O+10]), "=f"(d[O+11]), "=f"(d[O+12]), "=f"(d[O+13]), "=f"(d[O+14]), "=f"(d[O+15]), "=f"(d[O+16]), "=f"(d[O+17]), "=f"(d[O+18]), "=f"(d[O+19]), "=f"(d[O+20]), "=f"(d[O+21]), "=f"(d[O+22]), "=f"(d[O+23]), "=f"(d[O+24]), "=f"(d[O+25]), "=f"(d[O+26]), "=f"(d[O+27]), "=f"(d[O+28]), "=f"(d[O+29]), "=f"(d[O+30]), "=f"(d[O+31]), "=f"(d[O+32]), "=f"(d[O+33]), "=f"(d[O+34]), "=f"(d[O+35]), "=f"(d[O+36]), "=f"(d[O+37]), "=f"(d[O+38]), "=f"(d[O+39]), "=f"(d[O+40]), "=f"(d[O+41]), "=f"(d[O+42]), "=f"(d[O+43]), "=f"(d[O+44]), "=f"(d[O+45]), "=f"(d[O+46]), "=f"(d[O+47]), "=f"(d[O+48]), "=f"(d[O+49]), "=f"(d[O+50]), "=f"(d[O+51]), "=f"(d[O+52]), "=f"(d[O+53]), "=f"(d[O+54]), "=f"(d[O+55]), "=f"(d[O+56]), "=f"(d[O+57]), "=f"(d[O+58]), "=f"(d[O+59]), "=f"(d[O+60]), "=f"(d[O+61]), "=f"(d[O+62]), "=f"(d[O+63])
   : "r"(da), "r"(db), "n"(TB), "n"(HB), "n"(H128));
  else asm volatile("{\n.reg .pred p;\n.reg .b64 da, db;\nmov.b64 da, {%64, %68};\nmov.b64 db, {%65, %67};\nsetp.ne.b32 p, %69, 0;\nwgmma.mma_async.sync.aligned.m64n128k16.f32.bf16.bf16 {%0,%1,%2,%3,%4,%5,%6,%7,%8,%9,%10,%11,%12,%13,%14,%15,%16,%17,%18,%19,%20,%21,%22,%23,%24,%25,%26,%27,%28,%29,%30,%31,%32,%33,%34,%35,%36,%37,%38,%39,%40,%41,%42,%43,%44,%45,%46,%47,%48,%49,%50,%51,%52,%53,%54,%55,%56,%57,%58,%59,%60,%61,%62,%63}, da, db, p, 1, 1, 0, %66;\n}"
   : "+f"(d[O+0]), "+f"(d[O+1]), "+f"(d[O+2]), "+f"(d[O+3]), "+f"(d[O+4]), "+f"(d[O+5]), "+f"(d[O+6]), "+f"(d[O+7]), "+f"(d[O+8]), "+f"(d[O+9]), "+f"(d[O+10]), "+f"(d[O+11]), "+f"(d[O+12]), "+f"(d[O+13]), "+f"(d[O+14]), "+f"(d[O+15]), "+f"(d[O+16]), "+f"(d[O+17]), "+f"(d[O+18]), "+f"(d[O+19]), "+f"(d[O+20]), "+f"(d[O+21]), "+f"(d[O+22]), "+f"(d[O+23]), "+f"(d[O+24]), "+f"(d[O+25]), "+f"(d[O+26]), "+f"(d[O+27]), "+f"(d[O+28]), "+f"(d[O+29]), "+f"(d[O+30]), "+f"(d[O+31]), "+f"(d[O+32]), "+f"(d[O+33]), "+f"(d[O+34]), "+f"(d[O+35]), "+f"(d[O+36]), "+f"(d[O+37]), "+f"(d[O+38]), "+f"(d[O+39]), "+f"(d[O+40]), "+f"(d[O+41]), "+f"(d[O+42]), "+f"(d[O+43]), "+f"(d[O+44]), "+f"(d[O+45]), "+f"(d[O+46]), "+f"(d[O+47]), "+f"(d[O+48]), "+f"(d[O+49]), "+f"(d[O+50]), "+f"(d[O+51]), "+f"(d[O+52]), "+f"(d[O+53]), "+f"(d[O+54]), "+f"(d[O+55]), "+f"(d[O+56]), "+f"(d[O+57]), "+f"(d[O+58]), "+f"(d[O+59]), "+f"(d[O+60]), "+f"(d[O+61]), "+f"(d[O+62]), "+f"(d[O+63])
   : "r"(da), "r"(db), "n"(TB), "n"(HB), "n"(H128), "r"(sd));
}
template<int O,int TB,int ACC,uint32_t HB = H128,int NN> __device__ __forceinline__ void mma_rs128(float (&d)[NN], uint32_t a0, uint32_t a1, uint32_t a2, uint32_t a3, uint32_t db, int sd = 0){
  if constexpr (ACC == 1) asm volatile("{\n.reg .b64 db;\nmov.b64 db, {%68, %70};\nwgmma.mma_async.sync.aligned.m64n128k16.f32.bf16.bf16 {%0,%1,%2,%3,%4,%5,%6,%7,%8,%9,%10,%11,%12,%13,%14,%15,%16,%17,%18,%19,%20,%21,%22,%23,%24,%25,%26,%27,%28,%29,%30,%31,%32,%33,%34,%35,%36,%37,%38,%39,%40,%41,%42,%43,%44,%45,%46,%47,%48,%49,%50,%51,%52,%53,%54,%55,%56,%57,%58,%59,%60,%61,%62,%63}, {%64,%65,%66,%67}, db, 1, 1, 1, %69;\n}"
   : "+f"(d[O+0]), "+f"(d[O+1]), "+f"(d[O+2]), "+f"(d[O+3]), "+f"(d[O+4]), "+f"(d[O+5]), "+f"(d[O+6]), "+f"(d[O+7]), "+f"(d[O+8]), "+f"(d[O+9]), "+f"(d[O+10]), "+f"(d[O+11]), "+f"(d[O+12]), "+f"(d[O+13]), "+f"(d[O+14]), "+f"(d[O+15]), "+f"(d[O+16]), "+f"(d[O+17]), "+f"(d[O+18]), "+f"(d[O+19]), "+f"(d[O+20]), "+f"(d[O+21]), "+f"(d[O+22]), "+f"(d[O+23]), "+f"(d[O+24]), "+f"(d[O+25]), "+f"(d[O+26]), "+f"(d[O+27]), "+f"(d[O+28]), "+f"(d[O+29]), "+f"(d[O+30]), "+f"(d[O+31]), "+f"(d[O+32]), "+f"(d[O+33]), "+f"(d[O+34]), "+f"(d[O+35]), "+f"(d[O+36]), "+f"(d[O+37]), "+f"(d[O+38]), "+f"(d[O+39]), "+f"(d[O+40]), "+f"(d[O+41]), "+f"(d[O+42]), "+f"(d[O+43]), "+f"(d[O+44]), "+f"(d[O+45]), "+f"(d[O+46]), "+f"(d[O+47]), "+f"(d[O+48]), "+f"(d[O+49]), "+f"(d[O+50]), "+f"(d[O+51]), "+f"(d[O+52]), "+f"(d[O+53]), "+f"(d[O+54]), "+f"(d[O+55]), "+f"(d[O+56]), "+f"(d[O+57]), "+f"(d[O+58]), "+f"(d[O+59]), "+f"(d[O+60]), "+f"(d[O+61]), "+f"(d[O+62]), "+f"(d[O+63])
   : "r"(a0), "r"(a1), "r"(a2), "r"(a3), "r"(db), "n"(TB), "n"(HB));
  else if constexpr (ACC == 0) asm volatile("{\n.reg .b64 db;\nmov.b64 db, {%68, %70};\nwgmma.mma_async.sync.aligned.m64n128k16.f32.bf16.bf16 {%0,%1,%2,%3,%4,%5,%6,%7,%8,%9,%10,%11,%12,%13,%14,%15,%16,%17,%18,%19,%20,%21,%22,%23,%24,%25,%26,%27,%28,%29,%30,%31,%32,%33,%34,%35,%36,%37,%38,%39,%40,%41,%42,%43,%44,%45,%46,%47,%48,%49,%50,%51,%52,%53,%54,%55,%56,%57,%58,%59,%60,%61,%62,%63}, {%64,%65,%66,%67}, db, 0, 1, 1, %69;\n}"
   : "=f"(d[O+0]), "=f"(d[O+1]), "=f"(d[O+2]), "=f"(d[O+3]), "=f"(d[O+4]), "=f"(d[O+5]), "=f"(d[O+6]), "=f"(d[O+7]), "=f"(d[O+8]), "=f"(d[O+9]), "=f"(d[O+10]), "=f"(d[O+11]), "=f"(d[O+12]), "=f"(d[O+13]), "=f"(d[O+14]), "=f"(d[O+15]), "=f"(d[O+16]), "=f"(d[O+17]), "=f"(d[O+18]), "=f"(d[O+19]), "=f"(d[O+20]), "=f"(d[O+21]), "=f"(d[O+22]), "=f"(d[O+23]), "=f"(d[O+24]), "=f"(d[O+25]), "=f"(d[O+26]), "=f"(d[O+27]), "=f"(d[O+28]), "=f"(d[O+29]), "=f"(d[O+30]), "=f"(d[O+31]), "=f"(d[O+32]), "=f"(d[O+33]), "=f"(d[O+34]), "=f"(d[O+35]), "=f"(d[O+36]), "=f"(d[O+37]), "=f"(d[O+38]), "=f"(d[O+39]), "=f"(d[O+40]), "=f"(d[O+41]), "=f"(d[O+42]), "=f"(d[O+43]), "=f"(d[O+44]), "=f"(d[O+45]), "=f"(d[O+46]), "=f"(d[O+47]), "=f"(d[O+48]), "=f"(d[O+49]), "=f"(d[O+50]), "=f"(d[O+51]), "=f"(d[O+52]), "=f"(d[O+53]), "=f"(d[O+54]), "=f"(d[O+55]), "=f"(d[O+56]), "=f"(d[O+57]), "=f"(d[O+58]), "=f"(d[O+59]), "=f"(d[O+60]), "=f"(d[O+61]), "=f"(d[O+62]), "=f"(d[O+63])
   : "r"(a0), "r"(a1), "r"(a2), "r"(a3), "r"(db), "n"(TB), "n"(HB));
  else asm volatile("{\n.reg .pred p;\n.reg .b64 db;\nmov.b64 db, {%68, %70};\nsetp.ne.b32 p, %71, 0;\nwgmma.mma_async.sync.aligned.m64n128k16.f32.bf16.bf16 {%0,%1,%2,%3,%4,%5,%6,%7,%8,%9,%10,%11,%12,%13,%14,%15,%16,%17,%18,%19,%20,%21,%22,%23,%24,%25,%26,%27,%28,%29,%30,%31,%32,%33,%34,%35,%36,%37,%38,%39,%40,%41,%42,%43,%44,%45,%46,%47,%48,%49,%50,%51,%52,%53,%54,%55,%56,%57,%58,%59,%60,%61,%62,%63}, {%64,%65,%66,%67}, db, p, 1, 1, %69;\n}"
   : "+f"(d[O+0]), "+f"(d[O+1]), "+f"(d[O+2]), "+f"(d[O+3]), "+f"(d[O+4]), "+f"(d[O+5]), "+f"(d[O+6]), "+f"(d[O+7]), "+f"(d[O+8]), "+f"(d[O+9]), "+f"(d[O+10]), "+f"(d[O+11]), "+f"(d[O+12]), "+f"(d[O+13]), "+f"(d[O+14]), "+f"(d[O+15]), "+f"(d[O+16]), "+f"(d[O+17]), "+f"(d[O+18]), "+f"(d[O+19]), "+f"(d[O+20]), "+f"(d[O+21]), "+f"(d[O+22]), "+f"(d[O+23]), "+f"(d[O+24]), "+f"(d[O+25]), "+f"(d[O+26]), "+f"(d[O+27]), "+f"(d[O+28]), "+f"(d[O+29]), "+f"(d[O+30]), "+f"(d[O+31]), "+f"(d[O+32]), "+f"(d[O+33]), "+f"(d[O+34]), "+f"(d[O+35]), "+f"(d[O+36]), "+f"(d[O+37]), "+f"(d[O+38]), "+f"(d[O+39]), "+f"(d[O+40]), "+f"(d[O+41]), "+f"(d[O+42]), "+f"(d[O+43]), "+f"(d[O+44]), "+f"(d[O+45]), "+f"(d[O+46]), "+f"(d[O+47]), "+f"(d[O+48]), "+f"(d[O+49]), "+f"(d[O+50]), "+f"(d[O+51]), "+f"(d[O+52]), "+f"(d[O+53]), "+f"(d[O+54]), "+f"(d[O+55]), "+f"(d[O+56]), "+f"(d[O+57]), "+f"(d[O+58]), "+f"(d[O+59]), "+f"(d[O+60]), "+f"(d[O+61]), "+f"(d[O+62]), "+f"(d[O+63])
   : "r"(a0), "r"(a1), "r"(a2), "r"(a3), "r"(db), "n"(TB), "n"(HB), "r"(sd));
}

__host__ __device__ constexpr int brev(int a, int bits) { int r = 0; for (int i = 0; i < bits; i++) r |= ((a >> i) & 1) << (bits - 1 - i); return r; }
__host__ __device__ constexpr int ilog2(int n) { return n <= 1 ? 0 : 1 + ilog2(n / 2); }
template <int SG, int A> __device__ __forceinline__ void bfly(float2& a, float2& b) {
  if constexpr (A == 0) {
    float tr = a.x - b.x, ti = a.y - b.y; a.x += b.x; a.y += b.y; b.x = tr; b.y = ti;
  } else if constexpr (A == 8) {
    float pr = SG > 0 ? -b.y : b.y, pi = SG > 0 ? b.x : -b.x;
    b.x = a.x - pr; b.y = a.y - pi; a.x += pr; a.y += pi;
  } else {
    constexpr float wr = tbl::W32<A>::c, wi = SG * tbl::W32<A>::s;
    float tr = fmaf(wr, b.x, a.x), ti = fmaf(wr, b.y, a.y);
    tr = fmaf(-wi, b.y, tr); ti = fmaf(wi, b.x, ti);
    b.x = fmaf(2.f, a.x, -tr); b.y = fmaf(2.f, a.y, -ti); a.x = tr; a.y = ti;
  }
}
template <int SG, int N, int O, int ST, int A> __device__ __forceinline__ void dft_comb(float2 (&x)[32]) {
  if constexpr (A < N / 2) {
    constexpr int p = O + 2 * ST * brev(A, ilog2(N / 2));
    bfly<SG, A * (32 / N)>(x[p], x[p + ST]);
    dft_comb<SG, N, O, ST, A + 1>(x);
  }
}
template <int SG, int N, int O, int ST> __device__ __forceinline__ void dft(float2 (&x)[32]) {
  if constexpr (N > 1) {
    dft<SG, N / 2, O, 2 * ST>(x);
    dft<SG, N / 2, O + ST, 2 * ST>(x);
    dft_comb<SG, N, O, ST, 0>(x);
  }
}

#define MAPMODE 1
template <int V> struct IC { static constexpr int value = V; };
struct Maps { CUtensorMap x, ft, fg, e, g64, u64, g32, u32, d192, d32, wr, wi; };

constexpr int NCTA = 132;
constexpr int U = 16384;
constexpr int TB = 36864;
constexpr int OFF_RING = 8 * U, OFF_Z = 9 * U, OFF_WRAW = 12 * U, OFF_T = 13 * U;
constexpr int OFF_BAR = 14 * U;
constexpr int SMEM_BYTES = OFF_BAR + 512;
constexpr int B_FX = 0, B_FA = 8, B_FT = 12, B_Z = 16, B_W = 20;
constexpr int B_EA = 21, B_ET = 25, B_RDY = 29;
constexpr int B_T = 30, B_X1 = 31;

__global__ void __cluster_dims__(2, 1, 1) __launch_bounds__(512, 1)
fused_kernel(const __grid_constant__ Maps maps, const __nv_bfloat16* __restrict__ x, const __nv_bfloat16* __restrict__ w_r,
             const __nv_bfloat16* __restrict__ w_i, const __nv_bfloat16* __restrict__ gate_w, __nv_bfloat16* __restrict__ out) {
  extern __shared__ __align__(1024) uint8_t smem[];
  const uint32_t sb = smem_u32(smem);
  const uint32_t bars = sb + OFF_BAR;
  const int tid = threadIdx.x, lane = tid & 31;
  const int warp = __shfl_sync(0xffffffffu, tid >> 5, 0);
  const bool helper = blockIdx.x >= 128;
  const int cl = (blockIdx.x >> 1) & 63, rank = blockIdx.x & 1;
  const int q4 = (cl & 1) | ((cl >> 2) & 2), rb = ((cl >> 1) & 3) | ((cl >> 4) << 2);
  const int j = 2 * q4 + rank;
  const int f_full = 448 * q4 + (rank ? 256 : 0);
  const int f_half = 448 * q4 + (rank ? 224 : 192);
  const int kg = 2 * j + (rb >> 3), tn = rb & 7;

  if (tid == 64) { PROF_EV(0); PROF_CK(40); }
  if (warp == 0) {
    mbar_init(bars + 8 * lane, lane < B_EA ? 1 : lane < B_T ? 2 : lane == B_T ? 4 : 8);
    if (lane >= B_Z && lane < B_Z + 4) mbar_expect_tx(bars + 8 * lane, U);
    asm volatile("fence.mbarrier_init.release.cluster;" ::: "memory");
  } else if (warp == 15 && lane < 12) {
    asm volatile("prefetch.tensormap [%0];" ::"l"((const char*)&maps + lane * 128) : "memory");
  }
  if (tid == 0) PROF_EV(35);
  if (tid == 480) PROF_EV(36);
  __syncthreads();
  if (tid == 64) PROF_EV(37);
  asm volatile("barrier.cluster.arrive.relaxed.aligned;" ::: "memory");
  if (tid == 64) PROF_EV(38);

  if (warp >= 12) {
    asm volatile("setmaxnreg.dec.sync.aligned.u32 24;");
    if (lane == 0 && !helper) {
      if (warp == 12) PROF_EV(30);
      if (warp < 14) {
#pragma unroll 1
        for (int n = warp - 12; n < 36; n += 2) {
          const uint32_t fb = bars + 8 * (B_FA + (n & 3)), dst = sb + OFF_RING + (n & 3) * U;
          if (n >= 4) mbar_wait(bars + 8 * (B_EA + (n & 3)), ((n >> 2) & 1) ^ 1);
          mbar_expect_tx(fb, U);
          if (n < 8) {
            tma2d(dst, &maps.ft, fb, 64 * n, 64 * j);
            tma2d(dst + 8192, &maps.g32, fb, f_half, 64 * n);
            tma2d(dst + 12288, &maps.u32, fb, f_half, 64 * n);
          } else if (n == 9 || n == 10 || n >= 34) {
            tma4d(dst, &maps.e, fb, 0, 0, 0, 2 * rb + (n >= 34 ? n - 34 : n - 9));
          } else {
            const int q = n == 8 ? 0 : n - 10;
            tma2d(dst, &maps.g64, fb, f_full + 64 * (q >> 3), 64 * (q & 7));
            tma2d(dst + 8192, &maps.u64, fb, f_full + 64 * (q >> 3), 64 * (q & 7));
          }
        }
      } else if (warp == 14) {
#pragma unroll 1
        for (int q = 0; q < 8; q++) {
          mbar_expect_tx(bars + 8 * (B_FX + q), U);
          tma3d(sb + q * U, &maps.x, bars + 8 * (B_FX + q), 64 * q, 0, 2 * rb);
        }
        PROF_EV(31);
        mbar_wait(bars + 8 * (B_FX + 7), 0);
        PROF_EV(32);
        mbar_expect_tx(bars + 8 * B_W, 24576);
        tma4d(sb + OFF_WRAW, &maps.wr, bars + 8 * B_W, 16 * kg, 0, tn, 0);
        tma4d(sb + OFF_WRAW + 12288, &maps.wi, bars + 8 * B_W, 16 * kg, 0, tn, 0);
#pragma unroll 1
        for (int t = 0; t < 8; t++) {
          const int i = t < 3 ? t + 1 : t < 6 ? t - 2 : 0;
          const int col = 64 * (2 * ((q4 + i) & 3) + ((t < 3 || t == 6) ? 1 - rank : rank));
          const uint32_t fb = bars + 8 * (B_FT + (t & 3)), dst = sb + (t & 3) * TB;
          mbar_wait(bars + 8 * (B_ET + (t & 3)), t >> 2);
          mbar_expect_tx(fb, TB);
          tma2d(dst, &maps.d192, fb, col, f_full);
          tma2d(dst + 24576, &maps.d32, fb, col, f_half);
          tma4d(dst + 28672, &maps.fg, fb, col, 0, 0, 4 * j);
        }
      }
    }
  } else if (warp >= 8) {
    asm volatile("setmaxnreg.dec.sync.aligned.u32 88;");
    const int t = tid - 256, w = warp - 8;
    const float scale = 2.0f / (2048.0f * 512.0f);
    const uint32_t ep = ld_x1(&g_epoch[blockIdx.x * 8]);
    if (!helper) {
      uint4 xv[8], gv[2];
#pragma unroll
      for (int i = 0; i < 4; i++) {
        const int r = 16 * j + 4 * w + i;
        const uint4* p = (const uint4*)(x + (size_t)(2 * rb + (r >> 6) + 32 * (r & 63)) * 512) + lane;
        xv[2 * i] = __ldg(p); xv[2 * i + 1] = __ldg(p + 32);
      }
      gv[0] = __ldg((const uint4*)gate_w + lane); gv[1] = __ldg((const uint4*)gate_w + lane + 32);
      const uint32_t tag = (ep + 1) & 1;
      {
        float z[4];
#pragma unroll
        for (int i = 0; i < 4; i++) {
          float a = 0.f;
#pragma unroll
          for (int hh = 0; hh < 2; hh++) {
            const uint4 u = xv[2 * i + hh], v = gv[hh];
            a = fmaf(bf_lo(u.x), bf_lo(v.x), a); a = fmaf(bf_hi(u.x), bf_hi(v.x), a);
            a = fmaf(bf_lo(u.y), bf_lo(v.y), a); a = fmaf(bf_hi(u.y), bf_hi(v.y), a);
            a = fmaf(bf_lo(u.z), bf_lo(v.z), a); a = fmaf(bf_hi(u.z), bf_hi(v.z), a);
            a = fmaf(bf_lo(u.w), bf_lo(v.w), a); a = fmaf(bf_hi(u.w), bf_hi(v.w), a);
          }
#pragma unroll
          for (int o = 16; o; o >>= 1) a += __shfl_xor_sync(0xffffffffu, a, o);
          z[i] = a;
        }
        if (lane < 4) {
          const float zz = lane == 0 ? z[0] : lane == 1 ? z[1] : lane == 2 ? z[2] : z[3];
          asm volatile("st.relaxed.gpu.global.f32 [%0], %1;" ::"l"(g_gate + rb * 128 + 16 * j + 4 * w + lane), "f"(tagf(1.0f / (1.0f + __expf(-zz)), tag)) : "memory");
        }
        if (t == 0) PROF_EV(18);
      }
      if (w == 0) {
        const int c = lane >> 4, jj = 16 * blockIdx.x + (lane & 15), jm = (2048 - jj) & 2047;
        const unsigned short* pr = (const unsigned short*)w_r + 256 * c;
        const unsigned short* pi = (const unsigned short*)w_i + 256 * c;
        const float wr = 0.5f * (bf_lo(__ldg(pr + jj * 257)) + bf_lo(__ldg(pr + jm * 257)));
        const float wi = 0.5f * (bf_lo(__ldg(pi + jj * 257)) - bf_lo(__ldg(pi + jm * 257)));
        st_x2(g_Wh + c * 2048 + jj, tagf(c ? -wi : wr, tag), c ? wr : wi);
      }
      const int k = 16 * kg + (t & 15), j1 = 8 * tn + (t >> 4);
      {
        const unsigned short* p = (const unsigned short*)(smem + OFF_WRAW) + (t >> 4) * 25 + (t & 15);
        uint32_t wv[32];
        mbar_wait(bars + 8 * B_W, 0);
#pragma unroll
        for (int a = 0; a < 32; a++) wv[a] = (uint32_t)p[a * 192] | ((uint32_t)p[6144 + a * 192] << 16);
        asm volatile("bar.sync 1, 128;" ::: "memory");
#pragma unroll
        for (int a = 0; a < 8; a++) *(uint4*)(smem + OFF_WRAW + (a * 128 + t) * 16) = make_uint4(wv[4 * a], wv[4 * a + 1], wv[4 * a + 2], wv[4 * a + 3]);
      }
      if (t == 0) PROF_EV(11);
      mbar_wait(bars + 8 * B_X1, 0);
      float2 v[32];
      probe_tag(g_X1p + (size_t)(kg * 8 + tn) * 4096 + lane * 128 + w * 32 + 31, tag);
      if (t == 0) PROF_EV(22);
      load32_tagged(v, g_X1p + (size_t)(kg * 8 + tn) * 4096 + t, 128, tag);
      if (t == 0) PROF_EV(12);
      dft<-1, 32, 0, 1>(v);
      float2 y[32];
#pragma unroll
      for (int a4 = 0; a4 < 8; a4++) {
        const uint4 ww = *(const uint4*)(smem + OFF_WRAW + (a4 * 128 + t) * 16);
        const uint32_t wq[4] = {ww.x, ww.y, ww.z, ww.w};
#pragma unroll
        for (int e = 0; e < 4; e++) {
          const float2 z = v[brev(4 * a4 + e, 5)];
          const float wr = bf_lo(wq[e]), wi = bf_hi(wq[e]);
          y[4 * a4 + e] = make_float2(fmaf(z.x, wr, -z.y * wi), fmaf(z.x, wi, z.y * wr));
        }
      }
      dft<1, 32, 0, 1>(y);
      if (t == 0) PROF_EV(16);
      if (k != 0) {
        float2* dst = g_T + j1 * 256 + k;
#pragma unroll
        for (int a = 0; a < 32; a++) st_x2(dst + a * 64 * 256, tagf(y[brev(a, 5)].x, tag), y[brev(a, 5)].y);
      }
      if (t == 0) PROF_EV(17);
      {
        const uint4* src = (const uint4*)(g_T + (size_t)(2 * rb * 64 + (t >> 4)) * 256 + 32 * j) + (t & 15);
        uint4 u[16];
        probe_tag(g_T + (size_t)(2 * rb * 64 + 2 * w + 8 * (lane >> 1)) * 256 + 32 * j + (lane & 1) * 16, tag);
        if (t == 0) PROF_EV(23);
        const uint32_t t0 = (uint32_t)clock();
        for (;;) {
          uint32_t bad = 0;
#pragma unroll
          for (int a = 0; a < 16; a++) u[a] = ld_x4(src + a * 1024);
#pragma unroll
          for (int a = 0; a < 16; a++) bad |= (u[a].x ^ tag) | (u[a].z ^ tag);
          if (!__any_sync(0xffffffffu, bad & 1)) break;
          spin_guard(t0);
        }
        const int r = t >> 4, c = t & 15;
        const uint32_t dst = sb + OFF_T + r * 128 + (((c >> 1) ^ r) << 4) + (c & 1) * 8;
#pragma unroll
        for (int a = 0; a < 16; a++) {
          const uint32_t p0 = pack_bf16(__uint_as_float(u[a].x & ~1u) * scale, __uint_as_float(u[a].y) * scale);
          const uint32_t p1 = pack_bf16(__uint_as_float(u[a].z & ~1u) * scale, __uint_as_float(u[a].w) * scale);
          asm volatile("st.shared.v2.u32 [%0], {%1,%2};" ::"r"(dst + a * 1024), "r"(p0), "r"(p1) : "memory");
        }
        asm volatile("fence.proxy.async.shared::cta;" ::: "memory");
        __syncwarp();
        if (lane == 0) mbar_arrive(bars + 8 * B_T);
        if (t == 0) PROF_EV(13);
      }
    } else if (w == 0) {
      const uint32_t tag = (ep + 1) & 1;
      const int c = lane >> 4, j1 = 16 * (blockIdx.x - 128) + (lane & 15);
      float2* wf = (float2*)smem;
      float2 v[32];
      probe_tag(g_Wh + 16 * (blockIdx.x - 128) + 64 * lane, tag);
      load32_tagged(v, g_Wh + c * 2048 + j1, 64, tag);
#pragma unroll
      for (int a = 0; a < 32; a++) wf[a * 32 + lane] = v[a];
      if (t == 0) PROF_EV(11);
      probe_tag(g_X1s + 2048 + 16 * (blockIdx.x - 128) + 15 + 64 * lane, tag);
      load32_tagged(v, g_X1s + c * 2048 + j1, 64, tag);
      if (t == 0) PROF_EV(12);
      dft<-1, 32, 0, 1>(v);
      float2 y[32];
#pragma unroll
      for (int a = 0; a < 32; a++) {
        const float2 z = v[brev(a, 5)], wv = wf[a * 32 + lane];
        y[a] = make_float2(fmaf(z.x, wv.x, -z.y * wv.y), fmaf(z.x, wv.y, z.y * wv.x));
      }
      dft<1, 32, 0, 1>(y);
      if (t == 0) PROF_EV(16);
#pragma unroll
      for (int a = 0; a < 16; a++) {
        const float2 u0 = y[brev(2 * a, 5)], u1 = y[brev(2 * a + 1, 5)];
        const float2 keep = c ? u1 : u0, give = c ? u0 : u1;
        const float ox = __shfl_xor_sync(0xffffffffu, give.x, 16), oy = __shfl_xor_sync(0xffffffffu, give.y, 16);
        st_x2(g_T + ((2 * a + c) * 64 + j1) * 256, tagf((keep.x + ox) * 0.5f, tag), (keep.y + oy) * 0.5f);
      }
      if (t == 0) { g_epoch[blockIdx.x * 8] = ep + 1; PROF_EV(13); }
    }
  } else {
    asm volatile("setmaxnreg.inc.sync.aligned.u32 200;");
    if (!helper) {
      const int wg = warp >> 2, w = warp & 3, g = lane >> 2, q = lane & 3;
      const bool elect = (tid & 127) == 0;
      const uint32_t ep = ld_x1(&g_epoch[blockIdx.x * 8]);
      float c1[64], cA[64], c2[64], ci[64], ct[64];
      const int zero = blockIdx.x >> 16;
      uint32_t h[56], yf[16];
      const uint32_t d0 = (sb & 0x3FFFF) >> 4;
      const uint32_t dK = d0 | (1u << 16), dN = d0 | (512u << 16), dM = d0 | (256u << 16);
      const uint32_t dX = dK + wg * 512;
      constexpr uint32_t RING = OFF_RING >> 4;
      auto waitA = [&](int n) { mbar_wait(bars + 8 * (B_FA + (n & 3)), (n >> 2) & 1); };
      auto freeA = [&](int n) { if (elect) mbar_arrive(bars + 8 * (B_EA + (n & 3))); };

      auto c1_step = [&](auto first, int kb) {
        mbar_wait(bars + 8 * (B_FX + kb), 0); waitA(kb);
        wg_fence();
        const uint32_t dx = dX + kb * 1024, df = dK + RING + (kb & 3) * 1024, dm = dM + RING + 512 + (kb & 3) * 1024;
        mma_ss64<0, 0, decltype(first)::value>(c1, df, dx);
        mma_ss64<32, 1, decltype(first)::value, H64>(c1, dx, dm);
#pragma unroll
        for (int k = 1; k < 4; k++) {
          mma_ss64<0, 0, 1>(c1, df + k * 2, dx + k * 2);
          mma_ss64<32, 1, 1, H64>(c1, dx + k * 2, dm + k * 64);
        }
        wg_commit();
      };
      c1_step(IC<0>(), 0);
      if (tid == 0) PROF_EV(1);
#pragma unroll 1
      for (int kb = 1; kb < 8; kb++) { c1_step(IC<1>(), kb); wg_wait<1>(); freeA(kb - 1); }
      auto ffn_step = [&](auto first, float (&acc)[64], int n, int kb) {
        waitA(n);
        wg_fence();
        const uint32_t dx = dX + kb * 1024, db = dN + RING + (n & 3) * 1024;
        mma_ss128<0, 1, decltype(first)::value>(acc, dx, db, zero);
#pragma unroll
        for (int k = 1; k < 4; k++) mma_ss128<0, 1, 1>(acc, dx + k * 2, db + k * 128);
        wg_commit();
        wg_wait<1>();
      };
      const uint32_t tag = (ep + 1) & 1;
      const float* gp = g_gate + rb * 128 + wg * 64 + w * 16 + g;
      uint32_t gb0 = ld_x1(gp), gb1 = ld_x1(gp + 8);
      ffn_step(IC<0>(), c2, 8, 0);
      freeA(7);
      fence_regs<0, 64>(c1);
      if (tid == 0) PROF_EV(2);
#pragma unroll
      for (int i = 0; i < 16; i++) yf[i] = pack_pin(c1[2 * i], c1[2 * i + 1]);
      {
        const uint32_t t0 = (uint32_t)clock();
        while (((gb0 ^ tag) | (gb1 ^ tag)) & 1) { gb0 = ld_x1(gp); gb1 = ld_x1(gp + 8); spin_guard(t0); }
        __syncwarp();
      }
      if (tid == 0) PROF_EV(10);
      const float g0 = __uint_as_float(gb0 & ~1u), g1 = __uint_as_float(gb1 & ~1u);
      const float o0 = 1.0f - g0, o1 = 1.0f - g1;
#pragma unroll
      for (int i = 0; i < 8; i++) {
        const float o = (i & 1) ? o1 : o0;
        h[48 + i] = pack_pin(fmaxf(c1[32 + 2 * i], 0.f) * c1[48 + 2 * i] * o, fmaxf(c1[33 + 2 * i], 0.f) * c1[49 + 2 * i] * o);
      }
      {
        waitA(9); waitA(10);
        const uint32_t de = dN + RING + (1 + wg) * 1024;
        wg_fence();
        mma_rs128<0, 1, 0>(cA, yf[0], yf[1], yf[2], yf[3], de);
#pragma unroll
        for (int k = 1; k < 4; k++) mma_rs128<0, 1, 1>(cA, yf[4 * k], yf[4 * k + 1], yf[4 * k + 2], yf[4 * k + 3], de + k * 128);
        wg_commit();
        wg_wait<1>();
        freeA(8);
        ffn_step(IC<1>(), c2, 11, 1);
        freeA(9); freeA(10);
        fence_regs<0, 64>(cA);
        if (tid == 0) PROF_EV(19);
        const int s0 = 2 * rb + wg;
        float2* dst = g_X1p + ((size_t)((2 * j + (w >> 1)) * 8) * 32 + s0) * 128 + (2 * q) * 16 + 8 * (w & 1) + g;
#pragma unroll
        for (int n = 0; n < 8; n++) {
#pragma unroll
          for (int e = 0; e < 2; e++)
            st_x2(dst + n * 4096 + e * 16, tagf(cA[4 * n + e] - cA[34 + 4 * n + e], tag), cA[32 + 4 * n + e] + cA[4 * n + 2 + e]);
        }
        if (j == 0 && w == 0 && g == 0) {
#pragma unroll
          for (int n = 0; n < 8; n++) {
#pragma unroll
            for (int e = 0; e < 2; e++) {
              st_x2(g_X1s + s0 * 64 + 8 * n + 2 * q + e, tagf(cA[4 * n + e], tag), cA[32 + 4 * n + e]);
              st_x2(g_X1s + (32 + s0) * 64 + 8 * n + 2 * q + e, tagf(cA[4 * n + 2 + e], tag), cA[34 + 4 * n + e]);
            }
          }
        }
        __syncwarp();
        if (lane == 0) mbar_arrive(bars + 8 * B_X1);
        if (tid == 0) PROF_EV(3);
      }
      auto glu = [&](float (&acc)[64], int ho) {
#pragma unroll
        for (int i = 0; i < 16; i++) {
          const float o = (i & 1) ? o1 : o0;
          h[ho + i] = pack_pin(fmaxf(acc[2 * i], 0.f) * acc[32 + 2 * i] * o, fmaxf(acc[2 * i + 1], 0.f) * acc[33 + 2 * i] * o);
        }
      };
#pragma unroll 1
      for (int kb = 2; kb < 8; kb++) { ffn_step(IC<1>(), c2, 10 + kb, kb); freeA(9 + kb); }
      ffn_step(IC<2>(), cA, 18, 0); freeA(17);
      fence_regs<0, 64>(c2);
      if (tid == 0) PROF_EV(4);
      glu(c2, 0);
#pragma unroll 1
      for (int kb = 1; kb < 8; kb++) { ffn_step(IC<1>(), cA, 18 + kb, kb); freeA(17 + kb); }
      ffn_step(IC<2>(), c2, 26, 0); freeA(25);
      fence_regs<0, 64>(cA);
      if (tid == 0) PROF_EV(5);
      glu(cA, 16);
#pragma unroll 1
      for (int kb = 1; kb < 8; kb++) {
        ffn_step(IC<1>(), c2, 26 + kb, kb); freeA(25 + kb);
        if (elect && kb >= 3 && (kb & 1)) mbar_arrive(bars + 8 * (B_ET + ((kb - 3) >> 1)));
      }
      wg_wait<0>();
      if (elect) mbar_arrive(bars + 8 * (B_ET + 3));
      fence_regs<0, 64>(c2);
      glu(c2, 32);
      waitA(34 + wg);
      if (tid == 0) PROF_EV(6);
      mbar_wait(bars + 8 * B_T, 0);
      if (tid == 0) PROF_EV(7);
      wg_fence();
      {
        const uint32_t dt = dN + (OFF_T >> 4) + wg * 512, de = dK + RING + (2 + wg) * 1024;
        mma_ss64<0, 1, 0>(ci, de, dt);
        mma_ss64<32, 1, 0>(ci, de + 512, dt);
#pragma unroll
        for (int k = 1; k < 4; k++) {
          mma_ss64<0, 1, 1>(ci, de + k * 2, dt + k * 128);
          mma_ss64<32, 1, 1>(ci, de + (512 + k * 2), dt + k * 128);
        }
      }
      wg_commit();

      auto head = [&](auto off, int t) {
        constexpr int O = decltype(off)::value;
        mbar_wait(bars + 8 * (B_FT + (t & 3)), t >> 2);
        const uint32_t db = dN + (t & 3) * (TB >> 4);
        wg_fence();
        mma_rs64<O, 1, 0>(ct, h[0], h[1], h[2], h[3], db);
#pragma unroll
        for (int k = 1; k < 6; k++) mma_rs64<O, 1, 1>(ct, h[4 * k], h[4 * k + 1], h[4 * k + 2], h[4 * k + 3], db + k * 128);
        wg_commit();
        wg_wait<1>();
      };
      auto rest = [&](auto off, int t) {
        constexpr int O = decltype(off)::value;
        const uint32_t db = dN + (t & 3) * (TB >> 4);
        wg_fence();
#pragma unroll
        for (int k = 6; k < 14; k++) mma_rs64<O, 1, 1>(ct, h[4 * k], h[4 * k + 1], h[4 * k + 2], h[4 * k + 3], db + k * 128);
#pragma unroll
        for (int k = 0; k < 4; k++) mma_rs64<O, 1, 1>(ct, yf[4 * k], yf[4 * k + 1], yf[4 * k + 2], yf[4 * k + 3], db + (14 + k) * 128);
        wg_commit();
      };
      auto freeT = [&](int t) { if (elect) mbar_arrive(bars + 8 * (B_ET + t)); };
      const uint32_t peerZ = mapa(sb + OFF_Z + tid * 16, rank ^ 1), peerB = mapa(bars + 8 * B_Z, rank ^ 1);
      auto send_peer = [&](auto off, int z) {
        constexpr int O = decltype(off)::value;
        fence_regs<O, 32>(ct);
#pragma unroll
        for (int i = 0; i < 4; i++)
          asm volatile("st.async.weak.shared::cluster.mbarrier::complete_tx::bytes.v4.b32 [%0], {%1,%2,%3,%4}, [%5];" ::"r"(peerZ + z * U + i * 4096),
                       "r"(pack_bf16(ct[O + 8 * i], ct[O + 8 * i + 1])), "r"(pack_bf16(ct[O + 8 * i + 2], ct[O + 8 * i + 3])),
                       "r"(pack_bf16(ct[O + 8 * i + 4], ct[O + 8 * i + 5])), "r"(pack_bf16(ct[O + 8 * i + 6], ct[O + 8 * i + 7])), "r"(peerB + 8 * z) : "memory");
      };
      auto send_grid = [&](auto off, int z) {
        constexpr int O = decltype(off)::value;
        fence_regs<O, 32>(ct);
        mbar_wait(bars + 8 * (B_Z + z), 0);
        uint4* dst = g_part + (size_t)((rb * 8 + 2 * ((q4 + z + 1) & 3) + rank) * 3 + z) * 1024 + tid;
#pragma unroll
        for (int i = 0; i < 4; i++) {
          const uint4 p = *(const uint4*)(smem + OFF_Z + z * U + i * 4096 + tid * 16);
          st_x4(dst + i * 256, (pack_bf16(ct[O + 8 * i] + bf_lo(p.x), ct[O + 8 * i + 1] + bf_hi(p.x)) & ~1u) | tag,
                pack_bf16(ct[O + 8 * i + 2] + bf_lo(p.y), ct[O + 8 * i + 3] + bf_hi(p.y)),
                pack_bf16(ct[O + 8 * i + 4] + bf_lo(p.z), ct[O + 8 * i + 5] + bf_hi(p.z)),
                pack_bf16(ct[O + 8 * i + 6] + bf_lo(p.w), ct[O + 8 * i + 7] + bf_hi(p.w)));
        }
      };
      asm volatile("barrier.cluster.wait.aligned;" ::: "memory");
      head(IC<0>(), 0);
      if (elect) asm volatile("mbarrier.arrive.shared::cluster.b64 _, [%0];" ::"r"(mapa(bars + 8 * B_RDY, rank ^ 1)) : "memory");
      fence_regs<0, 64>(ci);
#pragma unroll
      for (int i = 0; i < 16; i++) {
        const float gg = (i & 1) ? g1 : g0;
        yf[i] = pack_pin((ci[2 * i] + ci[33 + 2 * i]) * gg, (ci[2 * i + 1] - ci[32 + 2 * i]) * gg);
      }
      rest(IC<0>(), 0);
      if (tid == 0) PROF_EV(8);
      head(IC<32>(), 1); freeT(0); mbar_wait(bars + 8 * B_RDY, 0); send_peer(IC<0>(), 0); rest(IC<32>(), 1);
      head(IC<0>(), 2); freeT(1); send_peer(IC<32>(), 1); rest(IC<0>(), 2);
      head(IC<32>(), 3); freeT(2); send_peer(IC<0>(), 2); rest(IC<32>(), 3);
      head(IC<0>(), 4); freeT(3); send_grid(IC<32>(), 0); rest(IC<0>(), 4);
      head(IC<32>(), 5); send_grid(IC<0>(), 1); rest(IC<32>(), 5);
      head(IC<0>(), 6); send_grid(IC<32>(), 2); rest(IC<0>(), 6);
      head(IC<32>(), 7); send_peer(IC<0>(), 3); rest(IC<32>(), 7);
      if (tid == 0) PROF_EV(9);
      {
        const uint4* src = g_part + (size_t)(rb * 8 + j) * 3 * 1024 + tid;
        uint4 pv[12];
        const uint32_t t0 = (uint32_t)clock();
        for (;;) {
          uint32_t bad = 0;
#pragma unroll
          for (int i = 0; i < 12; i++) pv[i] = ld_x4(src + i * 256);
#pragma unroll
          for (int i = 0; i < 12; i++) bad |= pv[i].x ^ tag;
          if (!__any_sync(0xffffffffu, bad & 1)) break;
          probe_tag(src - lane + ((lane & 3) == 3 ? 0 : (lane & 3)) * 1024 + 768, tag);
          spin_guard(t0);
        }
        if (tid == 0) PROF_EV(14);
        float sum[32];
#pragma unroll
        for (int i = 0; i < 4; i++) {
          const uint32_t a[4] = {pv[i].x & ~1u, pv[i].y, pv[i].z, pv[i].w}, b[4] = {pv[4 + i].x & ~1u, pv[4 + i].y, pv[4 + i].z, pv[4 + i].w},
                         c[4] = {pv[8 + i].x & ~1u, pv[8 + i].y, pv[8 + i].z, pv[8 + i].w};
#pragma unroll
          for (int e = 0; e < 4; e++) {
            sum[8 * i + 2 * e] = bf_lo(a[e]) + bf_lo(b[e]) + bf_lo(c[e]);
            sum[8 * i + 2 * e + 1] = bf_hi(a[e]) + bf_hi(b[e]) + bf_hi(c[e]);
          }
        }
        mbar_wait(bars + 8 * (B_Z + 3), 0);
#pragma unroll
        for (int i = 0; i < 4; i++) {
          const uint4 p = *(const uint4*)(smem + OFF_Z + 3 * U + i * 4096 + tid * 16);
          const uint32_t a[4] = {p.x, p.y, p.z, p.w};
#pragma unroll
          for (int e = 0; e < 4; e++) { sum[8 * i + 2 * e] += bf_lo(a[e]); sum[8 * i + 2 * e + 1] += bf_hi(a[e]); }
        }
        wg_wait<0>();
        fence_regs<32, 32>(ct);
#pragma unroll
        for (int i = 0; i < 32; i++) sum[i] += ct[32 + i];
        const uint32_t stg = sb + OFF_T + warp * 2048;
        const int mr = (lane & 7) + ((lane >> 3) & 1) * 8, mc = lane >> 4;
#pragma unroll
        for (int i = 0; i < 4; i++) {
          const uint32_t a = stg + mr * 128 + (((2 * i + mc) ^ (mr & 7)) << 4);
          asm volatile("stmatrix.sync.aligned.m8n8.x4.shared.b16 [%0], {%1,%2,%3,%4};" ::"r"(a), "r"(pack_bf16(sum[8 * i], sum[8 * i + 1])),
                       "r"(pack_bf16(sum[8 * i + 2], sum[8 * i + 3])), "r"(pack_bf16(sum[8 * i + 4], sum[8 * i + 5])),
                       "r"(pack_bf16(sum[8 * i + 6], sum[8 * i + 7])) : "memory");
        }
        __syncwarp();
#pragma unroll
        for (int i = 0; i < 4; i++) {
          const int r = 4 * i + (lane >> 3), c = lane & 7;
          const uint4 v = *(const uint4*)(smem + OFF_T + warp * 2048 + r * 128 + ((c ^ (r & 7)) << 4));
          *(uint4*)(out + (size_t)(2 * rb + wg + 32 * (16 * w + r)) * 512 + 64 * j + 8 * c) = v;
        }
      }
      if (tid == 0) { g_epoch[blockIdx.x * 8] = ep + 1; PROF_EV(15); PROF_CK(41); }
    }
  }
}

typedef CUresult (*EncodeFn)(CUtensorMap*, CUtensorMapDataType, cuuint32_t, void*, const cuuint64_t*, const cuuint64_t*, const cuuint32_t*,
                             const cuuint32_t*, CUtensorMapInterleave, CUtensorMapSwizzle, CUtensorMapL2promotion, CUtensorMapFloatOOBfill);

static void encode(EncodeFn f, CUtensorMap* m, const void* base, int rank, const cuuint64_t* dims, const cuuint64_t* strides, const cuuint32_t* box,
                   CUtensorMapSwizzle sw) {
  cuuint32_t es[5] = {1, 1, 1, 1, 1};
  f(m, CU_TENSOR_MAP_DATA_TYPE_BFLOAT16, rank, (void*)base, dims, strides, box, es, CU_TENSOR_MAP_INTERLEAVE_NONE, sw,
    CU_TENSOR_MAP_L2_PROMOTION_L2_128B, CU_TENSOR_MAP_FLOAT_OOB_FILL_NONE);
}

extern "C" void kernel_launch(void* const* d_in, const int* in_sizes, int n_in, void* d_out, int out_size) {
  (void)in_sizes; (void)n_in; (void)out_size;
  const __nv_bfloat16* x = (const __nv_bfloat16*)d_in[0];
  const __nv_bfloat16* w_r = (const __nv_bfloat16*)d_in[1];
  const __nv_bfloat16* w_i = (const __nv_bfloat16*)d_in[2];
  const __nv_bfloat16* Wg = (const __nv_bfloat16*)d_in[4];
  const __nv_bfloat16* Wu = (const __nv_bfloat16*)d_in[5];
  const __nv_bfloat16* Wd = (const __nv_bfloat16*)d_in[6];
  const __nv_bfloat16* gw = (const __nv_bfloat16*)d_in[7];

  void* fp = nullptr; cudaDriverEntryPointQueryResult qr;
  cudaGetDriverEntryPoint("cuTensorMapEncodeTiled", &fp, cudaEnableDefault, &qr);
  EncodeFn enc = (EncodeFn)fp;
  void *pFT, *pET;
  cudaGetSymbolAddress(&pFT, g_FT); cudaGetSymbolAddress(&pET, g_ET);

  Maps mp;
  const CUtensorMapSwizzle S128 = CU_TENSOR_MAP_SWIZZLE_128B, S64 = CU_TENSOR_MAP_SWIZZLE_64B;
  { cuuint64_t d[3] = {512, 64, 32}, s[2] = {32768, 1024}; cuuint32_t b[3] = {64, 64, 2}; encode(enc, &mp.x, x, 3, d, s, b, S128); }
  { cuuint64_t d[2] = {512, 512}, s[1] = {1024}; cuuint32_t b[2] = {64, 64}; encode(enc, &mp.ft, pFT, 2, d, s, b, S128); }
  { cuuint64_t d[4] = {512, 2, 8, 32}, s[3] = {8192, 1024, 16384}; cuuint32_t b[4] = {64, 2, 8, 4}; encode(enc, &mp.fg, pFT, 4, d, s, b, S128); }
  { cuuint64_t d[4] = {64, 64, 2, 32}, s[3] = {8192, 128, 256}; cuuint32_t b[4] = {64, 64, 2, 1}; encode(enc, &mp.e, pET, 4, d, s, b, S128); }
  { cuuint64_t d[2] = {1792, 512}, s[1] = {3584}; cuuint32_t b[2] = {64, 64}, b2[2] = {32, 64};
    encode(enc, &mp.g64, Wg, 2, d, s, b, S128); encode(enc, &mp.u64, Wu, 2, d, s, b, S128);
    encode(enc, &mp.g32, Wg, 2, d, s, b2, S64); encode(enc, &mp.u32, Wu, 2, d, s, b2, S64); }
  { cuuint64_t d[2] = {512, 1792}, s[1] = {1024}; cuuint32_t b[2] = {64, 192}, b2[2] = {64, 32};
    encode(enc, &mp.d192, Wd, 2, d, s, b, S128); encode(enc, &mp.d32, Wd, 2, d, s, b2, S128); }

  { cuuint64_t d[4] = {264, 8, 8, 32}, s[3] = {512, 4112, 32896}; cuuint32_t b[4] = {24, 8, 1, 32};
    encode(enc, &mp.wr, w_r, 4, d, s, b, CU_TENSOR_MAP_SWIZZLE_NONE); encode(enc, &mp.wi, w_i, 4, d, s, b, CU_TENSOR_MAP_SWIZZLE_NONE); }

  cudaFuncSetAttribute(fused_kernel, cudaFuncAttributeMaxDynamicSharedMemorySize, SMEM_BYTES);
  fused_kernel<<<NCTA, 512, SMEM_BYTES>>>(mp, x, w_r, w_i, gw, (__nv_bfloat16*)d_out);
}
```

```cpp
#include <cuda_runtime.h>
#include <cuda_bf16.h>
#include <cuda.h>
#include <stdint.h>

namespace tbl {
constexpr double PI = 3.14159265358979323846264338327950288;
constexpr double sin_s(double x) { double t = x, s = x; for (int n = 1; n < 12; n++) { t *= -x * x / ((2 * n) * (2 * n + 1)); s += t; } return s; }
constexpr double cos_s(double x) { double t = 1, s = 1; for (int n = 1; n < 12; n++) { t *= -x * x / ((2 * n - 1) * (2 * n)); s += t; } return s; }
constexpr double cos2048(int m) {
  m &= 2047; if (m > 1024) m = 2048 - m;
  bool neg = false; if (m > 512) { m = 1024 - m; neg = true; }
  double v = (m <= 256) ? cos_s(2 * PI * m / 2048) : sin_s(2 * PI * (512 - m) / 2048);
  return neg ? -v : v;
}
constexpr uint16_t to_bf16(double v) {
  if (v == 0) return 0;
  uint16_t s = 0; if (v < 0) { s = 0x8000; v = -v; }
  int e = 0; while (v >= 2) { v /= 2; e++; } while (v < 1) { v *= 2; e--; }
  double m = (v - 1) * 128; int mi = (int)m; double fr = m - mi;
  if (fr > 0.5 || (fr == 0.5 && (mi & 1))) mi++;
  if (mi == 128) { mi = 0; e++; }
  return (uint16_t)(s | ((e + 127) << 7) | mi);
}
struct CosT { uint16_t v[2048]; constexpr CosT() : v() { for (int i = 0; i < 2048; i++) v[i] = to_bf16(cos2048(i)); } };
struct alignas(1024) FT {
  uint16_t v[512 * 512];
  constexpr FT() : v() {
    CosT c;
    for (int r = 0; r < 512; r++) {
      int k = (r >> 4) * 8 + (r & 7), e = (r >> 3) & 1;
      int mul = 4 * k, add = e ? 512 : 0;
      if (k == 0 && e == 1) { mul = 1024; add = 0; }
      for (int d = 0; d < 512; d++) v[r * 512 + d] = c.v[(d * mul + add) & 2047];
    }
  }
};
struct alignas(1024) ET {
  uint16_t v[2048 * 128];
  constexpr ET() : v() {
    CosT c;
    for (int s = 0; s < 2048; s++)
      for (int j = 0; j < 64; j++) { v[s * 128 + j] = c.v[(s * j) & 2047]; v[s * 128 + 64 + j] = c.v[(s * j + 512) & 2047]; }
  }
};
template <int A> struct W32 {
  static constexpr float c = (float)cos2048(A * 64);
  static constexpr float s = (float)cos2048(A * 64 - 512);
};
}

__device__ constexpr tbl::FT g_FT = tbl::FT();
__device__ constexpr tbl::ET g_ET = tbl::ET();

__device__ __align__(1024) uint2 g_X1p[128 * 32 * 64];
__device__ __align__(1024) float2 g_X1s[2 * 32 * 64];
__device__ __align__(1024) uint2 g_T[8 * 16 * 2 * 64 * 16];
__device__ __align__(1024) uint4 g_part[128 * 3 * 1024];
__device__ __align__(16) float g_gate[16 * 128];
__device__ __align__(16) float2 g_Wh[2 * 2048];
__device__ unsigned g_epoch[132 * 8];
#define PROF_EV(i) do {} while (0)
#define PROF_CK(i) do {} while (0)

__device__ __forceinline__ uint32_t smem_u32(const void* p) { return (uint32_t)__cvta_generic_to_shared(p); }
__device__ __forceinline__ void mbar_init(uint32_t bar, uint32_t cnt) { asm volatile("mbarrier.init.shared::cta.b64 [%0], %1;" ::"r"(bar), "r"(cnt)); }
__device__ __forceinline__ void mbar_expect_tx(uint32_t bar, uint32_t bytes) { asm volatile("mbarrier.arrive.expect_tx.shared::cta.b64 _, [%0], %1;" ::"r"(bar), "r"(bytes) : "memory"); }
__device__ __forceinline__ void mbar_arrive(uint32_t bar) { asm volatile("mbarrier.arrive.shared::cta.b64 _, [%0];" ::"r"(bar) : "memory"); }
__device__ __forceinline__ bool mbar_try(uint32_t bar, uint32_t parity) {
  uint32_t ok;
  asm volatile("{\n.reg .pred p;\nmbarrier.try_wait.parity.shared::cta.b64 p, [%1], %2;\nselp.u32 %0, 1, 0, p;\n}" : "=r"(ok) : "r"(bar), "r"(parity) : "memory");
  return ok;
}
__device__ __forceinline__ void mbar_wait(uint32_t bar, uint32_t parity) {
  if (mbar_try(bar, parity)) return;
  const uint32_t t0 = (uint32_t)clock();
  while (!mbar_try(bar, parity)) { if ((uint32_t)clock() - t0 > (1u << 30)) __trap(); }
}
__device__ __forceinline__ void spin_guard(uint32_t t0) { if ((uint32_t)clock() - t0 > (1u << 30)) __trap(); }
__device__ __forceinline__ float tagf(float v, uint32_t tag) { return __uint_as_float((__float_as_uint(v) & ~1u) | tag); }
__device__ __forceinline__ float untag(float v) { return __uint_as_float(__float_as_uint(v) & ~1u); }
__device__ __forceinline__ void st_x2(float2* p, float a, float b) { asm volatile("st.relaxed.gpu.global.v2.f32 [%0], {%1,%2};" ::"l"(p), "f"(a), "f"(b) : "memory"); }
__device__ __forceinline__ float2 ld_x2(const float2* p) { float2 v; asm volatile("ld.relaxed.gpu.global.v2.f32 {%0,%1}, [%2];" : "=f"(v.x), "=f"(v.y) : "l"(p) : "memory"); return v; }
__device__ __forceinline__ void st_u2(uint2* p, uint32_t a, uint32_t b) { asm volatile("st.relaxed.gpu.global.v2.u32 [%0], {%1,%2};" ::"l"(p), "r"(a), "r"(b) : "memory"); }
__device__ __forceinline__ void prefetch2d(const CUtensorMap* m, int c0, int c1) { asm volatile("cp.async.bulk.prefetch.tensor.2d.L2.global [%0, {%1, %2}];" ::"l"(m), "r"(c0), "r"(c1) : "memory"); }
__device__ __forceinline__ void prefetch1d(const void* p, uint32_t bytes) { asm volatile("cp.async.bulk.prefetch.L2.global [%0], %1;" ::"l"(p), "r"(bytes) : "memory"); }
__device__ __forceinline__ uint32_t ld_x1(const void* p) { uint32_t v; asm volatile("ld.relaxed.gpu.global.u32 %0, [%1];" : "=r"(v) : "l"(p) : "memory"); return v; }
__device__ __forceinline__ uint4 ld_x4(const void* p) { uint4 v; asm volatile("ld.relaxed.gpu.global.v4.u32 {%0,%1,%2,%3}, [%4];" : "=r"(v.x), "=r"(v.y), "=r"(v.z), "=r"(v.w) : "l"(p) : "memory"); return v; }
__device__ __forceinline__ void st_x4(void* p, uint32_t a, uint32_t b, uint32_t c, uint32_t d) { asm volatile("st.relaxed.gpu.global.v4.u32 [%0], {%1,%2,%3,%4};" ::"l"(p), "r"(a), "r"(b), "r"(c), "r"(d) : "memory"); }
__device__ __forceinline__ uint32_t mapa(uint32_t a, uint32_t cta) { uint32_t r; asm volatile("mapa.shared::cluster.u32 %0, %1, %2;" : "=r"(r) : "r"(a), "r"(cta)); return r; }
__device__ __forceinline__ void probe_tag(const void* p, uint32_t tag) {
  const uint32_t t0 = (uint32_t)clock();
  while (__any_sync(0xffffffffu, (ld_x1(p) ^ tag) & 1)) { __nanosleep(64); spin_guard(t0); }
}
__device__ __forceinline__ void load32_tagged(float2 (&v)[32], const float2* src, int stride, uint32_t tag) {
  const uint32_t t0 = (uint32_t)clock();
  for (;;) {
    uint32_t bad = 0;
#pragma unroll
    for (int a = 0; a < 32; a++) v[a] = ld_x2(src + a * stride);
#pragma unroll
    for (int a = 0; a < 32; a++) bad |= __float_as_uint(v[a].x) ^ tag;
    if (!__any_sync(0xffffffffu, bad & 1)) break;
    spin_guard(t0);
  }
#pragma unroll
  for (int a = 0; a < 32; a++) v[a].x = untag(v[a].x);
}
__device__ __forceinline__ void tma2d(uint32_t dst, const CUtensorMap* m, uint32_t bar, int c0, int c1) {
  asm volatile("cp.async.bulk.tensor.2d.shared::cluster.global.mbarrier::complete_tx::bytes [%0], [%1, {%3, %4}], [%2];" ::"r"(dst), "l"(m), "r"(bar), "r"(c0), "r"(c1) : "memory");
}
__device__ __forceinline__ void tma3d(uint32_t dst, const CUtensorMap* m, uint32_t bar, int c0, int c1, int c2) {
  asm volatile("cp.async.bulk.tensor.3d.shared::cluster.global.mbarrier::complete_tx::bytes [%0], [%1, {%3, %4, %5}], [%2];" ::"r"(dst), "l"(m), "r"(bar), "r"(c0), "r"(c1), "r"(c2) : "memory");
}
__device__ __forceinline__ void tma4d(uint32_t dst, const CUtensorMap* m, uint32_t bar, int c0, int c1, int c2, int c3) {
  asm volatile("cp.async.bulk.tensor.4d.shared::cluster.global.mbarrier::complete_tx::bytes [%0], [%1, {%3, %4, %5, %6}], [%2];" ::"r"(dst), "l"(m), "r"(bar), "r"(c0), "r"(c1), "r"(c2), "r"(c3) : "memory");
}
__device__ __forceinline__ void wg_fence() { asm volatile("wgmma.fence.sync.aligned;" ::: "memory"); }
__device__ __forceinline__ void wg_commit() { asm volatile("wgmma.commit_group.sync.aligned;" ::: "memory"); }
template <int N> __device__ __forceinline__ void wg_wait() { asm volatile("wgmma.wait_group.sync.aligned %0;" ::"n"(N) : "memory"); }
template <int O, int N, int NN> __device__ __forceinline__ void fence_regs(float (&d)[NN]) {
#pragma unroll
  for (int i = 0; i < N; i++) asm volatile("" : "+f"(d[O + i])::"memory");
}
__device__ __forceinline__ uint32_t pack_bf16(float lo, float hi) {
  uint32_t r; asm("cvt.rn.bf16x2.f32 %0, %1, %2;" : "=r"(r) : "f"(hi), "f"(lo)); return r;
}
__device__ __forceinline__ uint32_t pack_pin(float lo, float hi) {
  uint32_t r; asm volatile("cvt.rn.bf16x2.f32 %0, %1, %2;" : "=r"(r) : "f"(hi), "f"(lo) : "memory"); return r;
}
__device__ __forceinline__ float bf_lo(uint32_t u) { return __uint_as_float(u << 16); }
__device__ __forceinline__ float bf_hi(uint32_t u) { return __uint_as_float(u & 0xffff0000u); }

constexpr uint32_t H128 = 0x40000040u;
constexpr uint32_t H64 = 0x80000020u;
template<int O,int TB,int ACC,uint32_t HB = H128,int NN> __device__ __forceinline__ void mma_ss64(float (&d)[NN], uint32_t da, uint32_t db, int sd = 0){
  if constexpr (ACC == 1) asm volatile("{\n.reg .b64 da, db;\nmov.b64 da, {%32, %36};\nmov.b64 db, {%33, %35};\nwgmma.mma_async.sync.aligned.m64n64k16.f32.bf16.bf16 {%0,%1,%2,%3,%4,%5,%6,%7,%8,%9,%10,%11,%12,%13,%14,%15,%16,%17,%18,%19,%20,%21,%22,%23,%24,%25,%26,%27,%28,%29,%30,%31}, da, db, 1, 1, 1, 0, %34;\n}"
   : "+f"(d[O+0]), "+f"(d[O+1]), "+f"(d[O+2]), "+f"(d[O+3]), "+f"(d[O+4]), "+f"(d[O+5]), "+f"(d[O+6]), "+f"(d[O+7]), "+f"(d[O+8]), "+f"(d[O+9]), "+f"(d[O+10]), "+f"(d[O+11]), "+f"(d[O+12]), "+f"(d[O+13]), "+f"(d[O+14]), "+f"(d[O+15]), "+f"(d[O+16]), "+f"(d[O+17]), "+f"(d[O+18]), "+f"(d[O+19]), "+f"(d[O+20]), "+f"(d[O+21]), "+f"(d[O+22]), "+f"(d[O+23]), "+f"(d[O+24]), "+f"(d[O+25]), "+f"(d[O+26]), "+f"(d[O+27]), "+f"(d[O+28]), "+f"(d[O+29]), "+f"(d[O+30]), "+f"(d[O+31])
   : "r"(da), "r"(db), "n"(TB), "n"(HB), "n"(H128));
  else if constexpr (ACC == 0) asm volatile("{\n.reg .b64 da, db;\nmov.b64 da, {%32, %36};\nmov.b64 db, {%33, %35};\nwgmma.mma_async.sync.aligned.m64n64k16.f32.bf16.bf16 {%0,%1,%2,%3,%4,%5,%6,%7,%8,%9,%10,%11,%12,%13,%14,%15,%16,%17,%18,%19,%20,%21,%22,%23,%24,%25,%26,%27,%28,%29,%30,%31}, da, db, 0, 1, 1, 0, %34;\n}"
   : "=f"(d[O+0]), "=f"(d[O+1]), "=f"(d[O+2]), "=f"(d[O+3]), "=f"(d[O+4]), "=f"(d[O+5]), "=f"(d[O+6]), "=f"(d[O+7]), "=f"(d[O+8]), "=f"(d[O+9]), "=f"(d[O+10]), "=f"(d[O+11]), "=f"(d[O+12]), "=f"(d[O+13]), "=f"(d[O+14]), "=f"(d[O+15]), "=f"(d[O+16]), "=f"(d[O+17]), "=f"(d[O+18]), "=f"(d[O+19]), "=f"(d[O+20]), "=f"(d[O+21]), "=f"(d[O+22]), "=f"(d[O+23]), "=f"(d[O+24]), "=f"(d[O+25]), "=f"(d[O+26]), "=f"(d[O+27]), "=f"(d[O+28]), "=f"(d[O+29]), "=f"(d[O+30]), "=f"(d[O+31])
   : "r"(da), "r"(db), "n"(TB), "n"(HB), "n"(H128));
  else asm volatile("{\n.reg .pred p;\n.reg .b64 da, db;\nmov.b64 da, {%32, %36};\nmov.b64 db, {%33, %35};\nsetp.ne.b32 p, %37, 0;\nwgmma.mma_async.sync.aligned.m64n64k16.f32.bf16.bf16 {%0,%1,%2,%3,%4,%5,%6,%7,%8,%9,%10,%11,%12,%13,%14,%15,%16,%17,%18,%19,%20,%21,%22,%23,%24,%25,%26,%27,%28,%29,%30,%31}, da, db, p, 1, 1, 0, %34;\n}"
   : "+f"(d[O+0]), "+f"(d[O+1]), "+f"(d[O+2]), "+f"(d[O+3]), "+f"(d[O+4]), "+f"(d[O+5]), "+f"(d[O+6]), "+f"(d[O+7]), "+f"(d[O+8]), "+f"(d[O+9]), "+f"(d[O+10]), "+f"(d[O+11]), "+f"(d[O+12]), "+f"(d[O+13]), "+f"(d[O+14]), "+f"(d[O+15]), "+f"(d[O+16]), "+f"(d[O+17]), "+f"(d[O+18]), "+f"(d[O+19]), "+f"(d[O+20]), "+f"(d[O+21]), "+f"(d[O+22]), "+f"(d[O+23]), "+f"(d[O+24]), "+f"(d[O+25]), "+f"(d[O+26]), "+f"(d[O+27]), "+f"(d[O+28]), "+f"(d[O+29]), "+f"(d[O+30]), "+f"(d[O+31])
   : "r"(da), "r"(db), "n"(TB), "n"(HB), "n"(H128), "r"(sd));
}
template<int O,int TB,int ACC,uint32_t HB = H128,int NN> __device__ __forceinline__ void mma_rs64(float (&d)[NN], uint32_t a0, uint32_t a1, uint32_t a2, uint32_t a3, uint32_t db, int sd = 0){
  if constexpr (ACC == 1) asm volatile("{\n.reg .b64 db;\nmov.b64 db, {%36, %38};\nwgmma.mma_async.sync.aligned.m64n64k16.f32.bf16.bf16 {%0,%1,%2,%3,%4,%5,%6,%7,%8,%9,%10,%11,%12,%13,%14,%15,%16,%17,%18,%19,%20,%21,%22,%23,%24,%25,%26,%27,%28,%29,%30,%31}, {%32,%33,%34,%35}, db, 1, 1, 1, %37;\n}"
   : "+f"(d[O+0]), "+f"(d[O+1]), "+f"(d[O+2]), "+f"(d[O+3]), "+f"(d[O+4]), "+f"(d[O+5]), "+f"(d[O+6]), "+f"(d[O+7]), "+f"(d[O+8]), "+f"(d[O+9]), "+f"(d[O+10]), "+f"(d[O+11]), "+f"(d[O+12]), "+f"(d[O+13]), "+f"(d[O+14]), "+f"(d[O+15]), "+f"(d[O+16]), "+f"(d[O+17]), "+f"(d[O+18]), "+f"(d[O+19]), "+f"(d[O+20]), "+f"(d[O+21]), "+f"(d[O+22]), "+f"(d[O+23]), "+f"(d[O+24]), "+f"(d[O+25]), "+f"(d[O+26]), "+f"(d[O+27]), "+f"(d[O+28]), "+f"(d[O+29]), "+f"(d[O+30]), "+f"(d[O+31])
   : "r"(a0), "r"(a1), "r"(a2), "r"(a3), "r"(db), "n"(TB), "n"(HB));
  else if constexpr (ACC == 0) asm volatile("{\n.reg .b64 db;\nmov.b64 db, {%36, %38};\nwgmma.mma_async.sync.aligned.m64n64k16.f32.bf16.bf16 {%0,%1,%2,%3,%4,%5,%6,%7,%8,%9,%10,%11,%12,%13,%14,%15,%16,%17,%18,%19,%20,%21,%22,%23,%24,%25,%26,%27,%28,%29,%30,%31}, {%32,%33,%34,%35}, db, 0, 1, 1, %37;\n}"
   : "=f"(d[O+0]), "=f"(d[O+1]), "=f"(d[O+2]), "=f"(d[O+3]), "=f"(d[O+4]), "=f"(d[O+5]), "=f"(d[O+6]), "=f"(d[O+7]), "=f"(d[O+8]), "=f"(d[O+9]), "=f"(d[O+10]), "=f"(d[O+11]), "=f"(d[O+12]), "=f"(d[O+13]), "=f"(d[O+14]), "=f"(d[O+15]), "=f"(d[O+16]), "=f"(d[O+17]), "=f"(d[O+18]), "=f"(d[O+19]), "=f"(d[O+20]), "=f"(d[O+21]), "=f"(d[O+22]), "=f"(d[O+23]), "=f"(d[O+24]), "=f"(d[O+25]), "=f"(d[O+26]), "=f"(d[O+27]), "=f"(d[O+28]), "=f"(d[O+29]), "=f"(d[O+30]), "=f"(d[O+31])
   : "r"(a0), "r"(a1), "r"(a2), "r"(a3), "r"(db), "n"(TB), "n"(HB));
  else asm volatile("{\n.reg .pred p;\n.reg .b64 db;\nmov.b64 db, {%36, %38};\nsetp.ne.b32 p, %39, 0;\nwgmma.mma_async.sync.aligned.m64n64k16.f32.bf16.bf16 {%0,%1,%2,%3,%4,%5,%6,%7,%8,%9,%10,%11,%12,%13,%14,%15,%16,%17,%18,%19,%20,%21,%22,%23,%24,%25,%26,%27,%28,%29,%30,%31}, {%32,%33,%34,%35}, db, p, 1, 1, %37;\n}"
   : "+f"(d[O+0]), "+f"(d[O+1]), "+f"(d[O+2]), "+f"(d[O+3]), "+f"(d[O+4]), "+f"(d[O+5]), "+f"(d[O+6]), "+f"(d[O+7]), "+f"(d[O+8]), "+f"(d[O+9]), "+f"(d[O+10]), "+f"(d[O+11]), "+f"(d[O+12]), "+f"(d[O+13]), "+f"(d[O+14]), "+f"(d[O+15]), "+f"(d[O+16]), "+f"(d[O+17]), "+f"(d[O+18]), "+f"(d[O+19]), "+f"(d[O+20]), "+f"(d[O+21]), "+f"(d[O+22]), "+f"(d[O+23]), "+f"(d[O+24]), "+f"(d[O+25]), "+f"(d[O+26]), "+f"(d[O+27]), "+f"(d[O+28]), "+f"(d[O+29]), "+f"(d[O+30]), "+f"(d[O+31])
   : "r"(a0), "r"(a1), "r"(a2), "r"(a3), "r"(db), "n"(TB), "n"(HB), "r"(sd));
}
template<int O,int TB,int ACC,uint32_t HB = H128,int NN> __device__ __forceinline__ void mma_ss128(float (&d)[NN], uint32_t da, uint32_t db, int sd = 0){
  if constexpr (ACC == 1) asm volatile("{\n.reg .b64 da, db;\nmov.b64 da, {%64, %68};\nmov.b64 db, {%65, %67};\nwgmma.mma_async.sync.aligned.m64n128k16.f32.bf16.bf16 {%0,%1,%2,%3,%4,%5,%6,%7,%8,%9,%10,%11,%12,%13,%14,%15,%16,%17,%18,%19,%20,%21,%22,%23,%24,%25,%26,%27,%28,%29,%30,%31,%32,%33,%34,%35,%36,%37,%38,%39,%40,%41,%42,%43,%44,%45,%46,%47,%48,%49,%50,%51,%52,%53,%54,%55,%56,%57,%58,%59,%60,%61,%62,%63}, da, db, 1, 1, 1, 0, %66;\n}"
   : "+f"(d[O+0]), "+f"(d[O+1]), "+f"(d[O+2]), "+f"(d[O+3]), "+f"(d[O+4]), "+f"(d[O+5]), "+f"(d[O+6]), "+f"(d[O+7]), "+f"(d[O+8]), "+f"(d[O+9]), "+f"(d[O+10]), "+f"(d[O+11]), "+f"(d[O+12]), "+f"(d[O+13]), "+f"(d[O+14]), "+f"(d[O+15]), "+f"(d[O+16]), "+f"(d[O+17]), "+f"(d[O+18]), "+f"(d[O+19]), "+f"(d[O+20]), "+f"(d[O+21]), "+f"(d[O+22]), "+f"(d[O+23]), "+f"(d[O+24]), "+f"(d[O+25]), "+f"(d[O+26]), "+f"(d[O+27]), "+f"(d[O+28]), "+f"(d[O+29]), "+f"(d[O+30]), "+f"(d[O+31]), "+f"(d[O+32]), "+f"(d[O+33]), "+f"(d[O+34]), "+f"(d[O+35]), "+f"(d[O+36]), "+f"(d[O+37]), "+f"(d[O+38]), "+f"(d[O+39]), "+f"(d[O+40]), "+f"(d[O+41]), "+f"(d[O+42]), "+f"(d[O+43]), "+f"(d[O+44]), "+f"(d[O+45]), "+f"(d[O+46]), "+f"(d[O+47]), "+f"(d[O+48]), "+f"(d[O+49]), "+f"(d[O+50]), "+f"(d[O+51]), "+f"(d[O+52]), "+f"(d[O+53]), "+f"(d[O+54]), "+f"(d[O+55]), "+f"(d[O+56]), "+f"(d[O+57]), "+f"(d[O+58]), "+f"(d[O+59]), "+f"(d[O+60]), "+f"(d[O+61]), "+f"(d[O+62]), "+f"(d[O+63])
   : "r"(da), "r"(db), "n"(TB), "n"(HB), "n"(H128));
  else if constexpr (ACC == 0) asm volatile("{\n.reg .b64 da, db;\nmov.b64 da, {%64, %68};\nmov.b64 db, {%65, %67};\nwgmma.mma_async.sync.aligned.m64n128k16.f32.bf16.bf16 {%0,%1,%2,%3,%4,%5,%6,%7,%8,%9,%10,%11,%12,%13,%14,%15,%16,%17,%18,%19,%20,%21,%22,%23,%24,%25,%26,%27,%28,%29,%30,%31,%32,%33,%34,%35,%36,%37,%38,%39,%40,%41,%42,%43,%44,%45,%46,%47,%48,%49,%50,%51,%52,%53,%54,%55,%56,%57,%58,%59,%60,%61,%62,%63}, da, db, 0, 1, 1, 0, %66;\n}"
   : "=f"(d[O+0]), "=f"(d[O+1]), "=f"(d[O+2]), "=f"(d[O+3]), "=f"(d[O+4]), "=f"(d[O+5]), "=f"(d[O+6]), "=f"(d[O+7]), "=f"(d[O+8]), "=f"(d[O+9]), "=f"(d[O+10]), "=f"(d[O+11]), "=f"(d[O+12]), "=f"(d[O+13]), "=f"(d[O+14]), "=f"(d[O+15]), "=f"(d[O+16]), "=f"(d[O+17]), "=f"(d[O+18]), "=f"(d[O+19]), "=f"(d[O+20]), "=f"(d[O+21]), "=f"(d[O+22]), "=f"(d[O+23]), "=f"(d[O+24]), "=f"(d[O+25]), "=f"(d[O+26]), "=f"(d[O+27]), "=f"(d[O+28]), "=f"(d[O+29]), "=f"(d[O+30]), "=f"(d[O+31]), "=f"(d[O+32]), "=f"(d[O+33]), "=f"(d[O+34]), "=f"(d[O+35]), "=f"(d[O+36]), "=f"(d[O+37]), "=f"(d[O+38]), "=f"(d[O+39]), "=f"(d[O+40]), "=f"(d[O+41]), "=f"(d[O+42]), "=f"(d[O+43]), "=f"(d[O+44]), "=f"(d[O+45]), "=f"(d[O+46]), "=f"(d[O+47]), "=f"(d[O+48]), "=f"(d[O+49]), "=f"(d[O+50]), "=f"(d[O+51]), "=f"(d[O+52]), "=f"(d[O+53]), "=f"(d[O+54]), "=f"(d[O+55]), "=f"(d[O+56]), "=f"(d[O+57]), "=f"(d[O+58]), "=f"(d[O+59]), "=f"(d[O+60]), "=f"(d[O+61]), "=f"(d[O+62]), "=f"(d[O+63])
   : "r"(da), "r"(db), "n"(TB), "n"(HB), "n"(H128));
  else asm volatile("{\n.reg .pred p;\n.reg .b64 da, db;\nmov.b64 da, {%64, %68};\nmov.b64 db, {%65, %67};\nsetp.ne.b32 p, %69, 0;\nwgmma.mma_async.sync.aligned.m64n128k16.f32.bf16.bf16 {%0,%1,%2,%3,%4,%5,%6,%7,%8,%9,%10,%11,%12,%13,%14,%15,%16,%17,%18,%19,%20,%21,%22,%23,%24,%25,%26,%27,%28,%29,%30,%31,%32,%33,%34,%35,%36,%37,%38,%39,%40,%41,%42,%43,%44,%45,%46,%47,%48,%49,%50,%51,%52,%53,%54,%55,%56,%57,%58,%59,%60,%61,%62,%63}, da, db, p, 1, 1, 0, %66;\n}"
   : "+f"(d[O+0]), "+f"(d[O+1]), "+f"(d[O+2]), "+f"(d[O+3]), "+f"(d[O+4]), "+f"(d[O+5]), "+f"(d[O+6]), "+f"(d[O+7]), "+f"(d[O+8]), "+f"(d[O+9]), "+f"(d[O+10]), "+f"(d[O+11]), "+f"(d[O+12]), "+f"(d[O+13]), "+f"(d[O+14]), "+f"(d[O+15]), "+f"(d[O+16]), "+f"(d[O+17]), "+f"(d[O+18]), "+f"(d[O+19]), "+f"(d[O+20]), "+f"(d[O+21]), "+f"(d[O+22]), "+f"(d[O+23]), "+f"(d[O+24]), "+f"(d[O+25]), "+f"(d[O+26]), "+f"(d[O+27]), "+f"(d[O+28]), "+f"(d[O+29]), "+f"(d[O+30]), "+f"(d[O+31]), "+f"(d[O+32]), "+f"(d[O+33]), "+f"(d[O+34]), "+f"(d[O+35]), "+f"(d[O+36]), "+f"(d[O+37]), "+f"(d[O+38]), "+f"(d[O+39]), "+f"(d[O+40]), "+f"(d[O+41]), "+f"(d[O+42]), "+f"(d[O+43]), "+f"(d[O+44]), "+f"(d[O+45]), "+f"(d[O+46]), "+f"(d[O+47]), "+f"(d[O+48]), "+f"(d[O+49]), "+f"(d[O+50]), "+f"(d[O+51]), "+f"(d[O+52]), "+f"(d[O+53]), "+f"(d[O+54]), "+f"(d[O+55]), "+f"(d[O+56]), "+f"(d[O+57]), "+f"(d[O+58]), "+f"(d[O+59]), "+f"(d[O+60]), "+f"(d[O+61]), "+f"(d[O+62]), "+f"(d[O+63])
   : "r"(da), "r"(db), "n"(TB), "n"(HB), "n"(H128), "r"(sd));
}
template<int O,int TB,int ACC,uint32_t HB = H128,int NN> __device__ __forceinline__ void mma_rs128(float (&d)[NN], uint32_t a0, uint32_t a1, uint32_t a2, uint32_t a3, uint32_t db, int sd = 0){
  if constexpr (ACC == 1) asm volatile("{\n.reg .b64 db;\nmov.b64 db, {%68, %70};\nwgmma.mma_async.sync.aligned.m64n128k16.f32.bf16.bf16 {%0,%1,%2,%3,%4,%5,%6,%7,%8,%9,%10,%11,%12,%13,%14,%15,%16,%17,%18,%19,%20,%21,%22,%23,%24,%25,%26,%27,%28,%29,%30,%31,%32,%33,%34,%35,%36,%37,%38,%39,%40,%41,%42,%43,%44,%45,%46,%47,%48,%49,%50,%51,%52,%53,%54,%55,%56,%57,%58,%59,%60,%61,%62,%63}, {%64,%65,%66,%67}, db, 1, 1, 1, %69;\n}"
   : "+f"(d[O+0]), "+f"(d[O+1]), "+f"(d[O+2]), "+f"(d[O+3]), "+f"(d[O+4]), "+f"(d[O+5]), "+f"(d[O+6]), "+f"(d[O+7]), "+f"(d[O+8]), "+f"(d[O+9]), "+f"(d[O+10]), "+f"(d[O+11]), "+f"(d[O+12]), "+f"(d[O+13]), "+f"(d[O+14]), "+f"(d[O+15]), "+f"(d[O+16]), "+f"(d[O+17]), "+f"(d[O+18]), "+f"(d[O+19]), "+f"(d[O+20]), "+f"(d[O+21]), "+f"(d[O+22]), "+f"(d[O+23]), "+f"(d[O+24]), "+f"(d[O+25]), "+f"(d[O+26]), "+f"(d[O+27]), "+f"(d[O+28]), "+f"(d[O+29]), "+f"(d[O+30]), "+f"(d[O+31]), "+f"(d[O+32]), "+f"(d[O+33]), "+f"(d[O+34]), "+f"(d[O+35]), "+f"(d[O+36]), "+f"(d[O+37]), "+f"(d[O+38]), "+f"(d[O+39]), "+f"(d[O+40]), "+f"(d[O+41]), "+f"(d[O+42]), "+f"(d[O+43]), "+f"(d[O+44]), "+f"(d[O+45]), "+f"(d[O+46]), "+f"(d[O+47]), "+f"(d[O+48]), "+f"(d[O+49]), "+f"(d[O+50]), "+f"(d[O+51]), "+f"(d[O+52]), "+f"(d[O+53]), "+f"(d[O+54]), "+f"(d[O+55]), "+f"(d[O+56]), "+f"(d[O+57]), "+f"(d[O+58]), "+f"(d[O+59]), "+f"(d[O+60]), "+f"(d[O+61]), "+f"(d[O+62]), "+f"(d[O+63])
   : "r"(a0), "r"(a1), "r"(a2), "r"(a3), "r"(db), "n"(TB), "n"(HB));
  else if constexpr (ACC == 0) asm volatile("{\n.reg .b64 db;\nmov.b64 db, {%68, %70};\nwgmma.mma_async.sync.aligned.m64n128k16.f32.bf16.bf16 {%0,%1,%2,%3,%4,%5,%6,%7,%8,%9,%10,%11,%12,%13,%14,%15,%16,%17,%18,%19,%20,%21,%22,%23,%24,%25,%26,%27,%28,%29,%30,%31,%32,%33,%34,%35,%36,%37,%38,%39,%40,%41,%42,%43,%44,%45,%46,%47,%48,%49,%50,%51,%52,%53,%54,%55,%56,%57,%58,%59,%60,%61,%62,%63}, {%64,%65,%66,%67}, db, 0, 1, 1, %69;\n}"
   : "=f"(d[O+0]), "=f"(d[O+1]), "=f"(d[O+2]), "=f"(d[O+3]), "=f"(d[O+4]), "=f"(d[O+5]), "=f"(d[O+6]), "=f"(d[O+7]), "=f"(d[O+8]), "=f"(d[O+9]), "=f"(d[O+10]), "=f"(d[O+11]), "=f"(d[O+12]), "=f"(d[O+13]), "=f"(d[O+14]), "=f"(d[O+15]), "=f"(d[O+16]), "=f"(d[O+17]), "=f"(d[O+18]), "=f"(d[O+19]), "=f"(d[O+20]), "=f"(d[O+21]), "=f"(d[O+22]), "=f"(d[O+23]), "=f"(d[O+24]), "=f"(d[O+25]), "=f"(d[O+26]), "=f"(d[O+27]), "=f"(d[O+28]), "=f"(d[O+29]), "=f"(d[O+30]), "=f"(d[O+31]), "=f"(d[O+32]), "=f"(d[O+33]), "=f"(d[O+34]), "=f"(d[O+35]), "=f"(d[O+36]), "=f"(d[O+37]), "=f"(d[O+38]), "=f"(d[O+39]), "=f"(d[O+40]), "=f"(d[O+41]), "=f"(d[O+42]), "=f"(d[O+43]), "=f"(d[O+44]), "=f"(d[O+45]), "=f"(d[O+46]), "=f"(d[O+47]), "=f"(d[O+48]), "=f"(d[O+49]), "=f"(d[O+50]), "=f"(d[O+51]), "=f"(d[O+52]), "=f"(d[O+53]), "=f"(d[O+54]), "=f"(d[O+55]), "=f"(d[O+56]), "=f"(d[O+57]), "=f"(d[O+58]), "=f"(d[O+59]), "=f"(d[O+60]), "=f"(d[O+61]), "=f"(d[O+62]), "=f"(d[O+63])
   : "r"(a0), "r"(a1), "r"(a2), "r"(a3), "r"(db), "n"(TB), "n"(HB));
  else asm volatile("{\n.reg .pred p;\n.reg .b64 db;\nmov.b64 db, {%68, %70};\nsetp.ne.b32 p, %71, 0;\nwgmma.mma_async.sync.aligned.m64n128k16.f32.bf16.bf16 {%0,%1,%2,%3,%4,%5,%6,%7,%8,%9,%10,%11,%12,%13,%14,%15,%16,%17,%18,%19,%20,%21,%22,%23,%24,%25,%26,%27,%28,%29,%30,%31,%32,%33,%34,%35,%36,%37,%38,%39,%40,%41,%42,%43,%44,%45,%46,%47,%48,%49,%50,%51,%52,%53,%54,%55,%56,%57,%58,%59,%60,%61,%62,%63}, {%64,%65,%66,%67}, db, p, 1, 1, %69;\n}"
   : "+f"(d[O+0]), "+f"(d[O+1]), "+f"(d[O+2]), "+f"(d[O+3]), "+f"(d[O+4]), "+f"(d[O+5]), "+f"(d[O+6]), "+f"(d[O+7]), "+f"(d[O+8]), "+f"(d[O+9]), "+f"(d[O+10]), "+f"(d[O+11]), "+f"(d[O+12]), "+f"(d[O+13]), "+f"(d[O+14]), "+f"(d[O+15]), "+f"(d[O+16]), "+f"(d[O+17]), "+f"(d[O+18]), "+f"(d[O+19]), "+f"(d[O+20]), "+f"(d[O+21]), "+f"(d[O+22]), "+f"(d[O+23]), "+f"(d[O+24]), "+f"(d[O+25]), "+f"(d[O+26]), "+f"(d[O+27]), "+f"(d[O+28]), "+f"(d[O+29]), "+f"(d[O+30]), "+f"(d[O+31]), "+f"(d[O+32]), "+f"(d[O+33]), "+f"(d[O+34]), "+f"(d[O+35]), "+f"(d[O+36]), "+f"(d[O+37]), "+f"(d[O+38]), "+f"(d[O+39]), "+f"(d[O+40]), "+f"(d[O+41]), "+f"(d[O+42]), "+f"(d[O+43]), "+f"(d[O+44]), "+f"(d[O+45]), "+f"(d[O+46]), "+f"(d[O+47]), "+f"(d[O+48]), "+f"(d[O+49]), "+f"(d[O+50]), "+f"(d[O+51]), "+f"(d[O+52]), "+f"(d[O+53]), "+f"(d[O+54]), "+f"(d[O+55]), "+f"(d[O+56]), "+f"(d[O+57]), "+f"(d[O+58]), "+f"(d[O+59]), "+f"(d[O+60]), "+f"(d[O+61]), "+f"(d[O+62]), "+f"(d[O+63])
   : "r"(a0), "r"(a1), "r"(a2), "r"(a3), "r"(db), "n"(TB), "n"(HB), "r"(sd));
}

__host__ __device__ constexpr int brev(int a, int bits) { int r = 0; for (int i = 0; i < bits; i++) r |= ((a >> i) & 1) << (bits - 1 - i); return r; }
__host__ __device__ constexpr int ilog2(int n) { return n <= 1 ? 0 : 1 + ilog2(n / 2); }
template <int SG, int A> __device__ __forceinline__ void bfly(float2& a, float2& b) {
  if constexpr (A == 0) {
    float tr = a.x - b.x, ti = a.y - b.y; a.x += b.x; a.y += b.y; b.x = tr; b.y = ti;
  } else if constexpr (A == 8) {
    float pr = SG > 0 ? -b.y : b.y, pi = SG > 0 ? b.x : -b.x;
    b.x = a.x - pr; b.y = a.y - pi; a.x += pr; a.y += pi;
  } else {
    constexpr float wr = tbl::W32<A>::c, wi = SG * tbl::W32<A>::s;
    float tr = fmaf(wr, b.x, a.x), ti = fmaf(wr, b.y, a.y);
    tr = fmaf(-wi, b.y, tr); ti = fmaf(wi, b.x, ti);
    b.x = fmaf(2.f, a.x, -tr); b.y = fmaf(2.f, a.y, -ti); a.x = tr; a.y = ti;
  }
}
template <int SG, int N, int O, int ST, int A> __device__ __forceinline__ void dft_comb(float2 (&x)[32]) {
  if constexpr (A < N / 2) {
    constexpr int p = O + 2 * ST * brev(A, ilog2(N / 2));
    bfly<SG, A * (32 / N)>(x[p], x[p + ST]);
    dft_comb<SG, N, O, ST, A + 1>(x);
  }
}
template <int SG, int N, int O, int ST> __device__ __forceinline__ void dft(float2 (&x)[32]) {
  if constexpr (N > 1) {
    dft<SG, N / 2, O, 2 * ST>(x);
    dft<SG, N / 2, O + ST, 2 * ST>(x);
    dft_comb<SG, N, O, ST, 0>(x);
  }
}

#define XPACE 0
#define PFMODE 1
#define MAPMODE 0
template <int V> struct IC { static constexpr int value = V; };
struct Maps { CUtensorMap x, ft, fg, e, g64, u64, g32, u32, d192, d32, wr, wi; };

constexpr int NCTA = 132;
constexpr int U = 16384;
constexpr int TB = 36864;
constexpr int OFF_RING = 8 * U, OFF_Z = 9 * U, OFF_WRAW = 12 * U, OFF_T = 13 * U;
constexpr int OFF_BAR = 14 * U;
constexpr int SMEM_BYTES = OFF_BAR + 512;
constexpr int B_FX = 0, B_FA = 8, B_FT = 12, B_Z = 16, B_W = 20;
constexpr int B_EA = 21, B_ET = 25, B_RDY = 29;
constexpr int B_T = 30, B_X1 = 31;

__global__ void __cluster_dims__(2, 1, 1) __launch_bounds__(512, 1)
fused_kernel(const __grid_constant__ Maps maps, const __nv_bfloat16* __restrict__ x, const __nv_bfloat16* __restrict__ w_r,
             const __nv_bfloat16* __restrict__ w_i, const __nv_bfloat16* __restrict__ gate_w, const __nv_bfloat16* __restrict__ Wd,
             __nv_bfloat16* __restrict__ out) {
  extern __shared__ __align__(1024) uint8_t smem[];
  const uint32_t sb = smem_u32(smem);
  const uint32_t bars = sb + OFF_BAR;
  const int tid = threadIdx.x, lane = tid & 31;
  const int warp = __shfl_sync(0xffffffffu, tid >> 5, 0);
  const bool helper = blockIdx.x >= 128;
  const int cl = (blockIdx.x >> 1) & 63, rank = blockIdx.x & 1;
  const int q4 = cl & 3, rb = cl >> 2;
  const int j = 2 * q4 + rank;
  const int f_full = 448 * q4 + (rank ? 256 : 0);
  const int f_half = 448 * q4 + (rank ? 224 : 192);
  const int kg = 2 * j + (rb >> 3), tn = rb & 7;

  if (tid == 64) { PROF_EV(0); PROF_CK(40); }
  auto ring_load = [&](int n) {
    const uint32_t fb = bars + 8 * (B_FA + (n & 3)), dst = sb + OFF_RING + (n & 3) * U;
    mbar_expect_tx(fb, U);
    if (n < 8) {
      tma2d(dst, &maps.ft, fb, 64 * n, 64 * j);
      tma2d(dst + 8192, &maps.g32, fb, f_half, 64 * n);
      tma2d(dst + 12288, &maps.u32, fb, f_half, 64 * n);
    } else if (n == 9 || n == 10 || n >= 34) {
      tma4d(dst, &maps.e, fb, 0, 0, 0, 2 * rb + (n >= 34 ? n - 34 : n - 9));
    } else {
      const int q = n == 8 ? 0 : n - 10;
      tma2d(dst, &maps.g64, fb, f_full + 64 * (q >> 3), 64 * (q & 7));
      tma2d(dst + 8192, &maps.u64, fb, f_full + 64 * (q >> 3), 64 * (q & 7));
    }
  };
  auto x_load = [&](int q) {
    mbar_expect_tx(bars + 8 * (B_FX + q), U);
    tma3d(sb + q * U, &maps.x, bars + 8 * (B_FX + q), 64 * q, 0, 2 * rb);
  };
  if (warp >= 12 && lane == 0) {
    if (warp < 14) {
      const int p = warp - 12;
      mbar_init(bars + 8 * (B_FX + p), 1); mbar_init(bars + 8 * (B_FA + p), 1);
      mbar_init(bars + 8 * (B_FX + p + 2), 1); mbar_init(bars + 8 * (B_FA + p + 2), 1);
      asm volatile("fence.proxy.async.shared::cta;" ::: "memory");
      if (!helper) { x_load(p); ring_load(p); }
    } else if (warp == 14) {
#pragma unroll
      for (int i = 4; i < 8; i++) mbar_init(bars + 8 * (B_FX + i), 1);
    } else {
#pragma unroll
      for (int i = B_FT; i < 32; i++) mbar_init(bars + 8 * i, i < B_EA ? 1 : i < B_T ? 2 : i == B_T ? 4 : 8);
#pragma unroll
      for (int i = 0; i < 4; i++) mbar_expect_tx(bars + 8 * (B_Z + i), U);
      asm volatile("fence.mbarrier_init.release.cluster;" ::: "memory");
    }
  }
  __syncthreads();
  asm volatile("barrier.cluster.arrive.relaxed.aligned;" ::: "memory");
  if (tid == 64) PROF_EV(38);

  if (warp >= 12) {
    asm volatile("setmaxnreg.dec.sync.aligned.u32 24;");
    if (lane == 0 && !helper) {
      if (warp == 12) PROF_EV(30);
      if (warp < 14) {
#pragma unroll 1
        for (int n = warp - 10; n < 36; n += 2) {
          if (n >= 4) mbar_wait(bars + 8 * (B_EA + (n & 3)), ((n >> 2) & 1) ^ 1);
          else x_load(n);
          ring_load(n);
        }
      } else if (warp == 14) {
        mbar_wait(bars + 8 * (B_FX + XPACE), 0);
#pragma unroll 1
        for (int q = 4; q < 8; q++) x_load(q);
        PROF_EV(31);
        mbar_wait(bars + 8 * (B_FX + 7), 0);
        PROF_EV(32);
        prefetch2d(rb < 8 ? &maps.g64 : &maps.u64, f_full, 64 * (rb & 7));
        prefetch2d(&maps.g64, f_full + 64 + 64 * (rb >> 3), 64 * (rb & 7));
        prefetch2d(&maps.u64, f_full + 64 + 64 * (rb >> 3), 64 * (rb & 7));
        mbar_expect_tx(bars + 8 * B_W, 24576);
        tma4d(sb + OFF_WRAW, &maps.wr, bars + 8 * B_W, 16 * kg, 0, tn, 0);
        tma4d(sb + OFF_WRAW + 12288, &maps.wi, bars + 8 * B_W, 16 * kg, 0, tn, 0);
        prefetch1d(Wd + (size_t)(224 * j + 14 * rb) * 512, 14336);
#pragma unroll 1
        for (int t = 0; t < 8; t++) {
          const int i = t < 3 ? t + 1 : t < 6 ? t - 2 : 0;
          const int col = 64 * (2 * ((q4 + i) & 3) + ((t < 3 || t == 6) ? 1 - rank : rank));
          const uint32_t fb = bars + 8 * (B_FT + (t & 3)), dst = sb + (t & 3) * TB;
          mbar_wait(bars + 8 * (B_ET + (t & 3)), t >> 2);
          mbar_expect_tx(fb, TB);
          tma2d(dst, &maps.d192, fb, col, f_full);
          tma2d(dst + 24576, &maps.d32, fb, col, f_half);
          tma4d(dst + 28672, &maps.fg, fb, col, 0, 0, 4 * j);
        }
      }
    }
  } else if (warp >= 8) {
    asm volatile("setmaxnreg.dec.sync.aligned.u32 88;");
    const int t = tid - 256, w = warp - 8;
    const float scale = 2.0f / (2048.0f * 512.0f);
    const uint32_t ep = ld_x1(&g_epoch[blockIdx.x * 8]);
    if (!helper) {
      uint4 xv[8], gv[2];
#pragma unroll
      for (int i = 0; i < 4; i++) {
        const int r = 16 * j + 4 * w + i;
        const uint4* p = (const uint4*)(x + (size_t)(2 * rb + (r >> 6) + 32 * (r & 63)) * 512) + lane;
        xv[2 * i] = __ldg(p); xv[2 * i + 1] = __ldg(p + 32);
      }
      gv[0] = __ldg((const uint4*)gate_w + lane); gv[1] = __ldg((const uint4*)gate_w + lane + 32);
      const uint32_t tag = (ep + 1) & 1;
      {
        float z[4];
#pragma unroll
        for (int i = 0; i < 4; i++) {
          float a = 0.f;
#pragma unroll
          for (int hh = 0; hh < 2; hh++) {
            const uint4 u = xv[2 * i + hh], v = gv[hh];
            a = fmaf(bf_lo(u.x), bf_lo(v.x), a); a = fmaf(bf_hi(u.x), bf_hi(v.x), a);
            a = fmaf(bf_lo(u.y), bf_lo(v.y), a); a = fmaf(bf_hi(u.y), bf_hi(v.y), a);
            a = fmaf(bf_lo(u.z), bf_lo(v.z), a); a = fmaf(bf_hi(u.z), bf_hi(v.z), a);
            a = fmaf(bf_lo(u.w), bf_lo(v.w), a); a = fmaf(bf_hi(u.w), bf_hi(v.w), a);
          }
#pragma unroll
          for (int o = 16; o; o >>= 1) a += __shfl_xor_sync(0xffffffffu, a, o);
          z[i] = a;
        }
        if (lane < 4) {
          const float zz = lane == 0 ? z[0] : lane == 1 ? z[1] : lane == 2 ? z[2] : z[3];
          asm volatile("st.relaxed.gpu.global.f32 [%0], %1;" ::"l"(g_gate + rb * 128 + 16 * j + 4 * w + lane), "f"(tagf(1.0f / (1.0f + __expf(-zz)), tag)) : "memory");
        }
        if (t == 0) PROF_EV(18);
      }
      if (w == 0) {
        const int c = lane >> 4, jj = 16 * blockIdx.x + (lane & 15), jm = (2048 - jj) & 2047;
        const unsigned short* pr = (const unsigned short*)w_r + 256 * c;
        const unsigned short* pi = (const unsigned short*)w_i + 256 * c;
        const float wr = 0.5f * (bf_lo(__ldg(pr + jj * 257)) + bf_lo(__ldg(pr + jm * 257)));
        const float wi = 0.5f * (bf_lo(__ldg(pi + jj * 257)) - bf_lo(__ldg(pi + jm * 257)));
        st_x2(g_Wh + c * 2048 + jj, tagf(c ? -wi : wr, tag), c ? wr : wi);
      }
      const int k = 16 * kg + (t & 15), j1 = 8 * tn + (t >> 4);
      {
        const unsigned short* p = (const unsigned short*)(smem + OFF_WRAW) + (t >> 4) * 25 + (t & 15);
        uint32_t wv[32];
        mbar_wait(bars + 8 * B_W, 0);
#pragma unroll
        for (int a = 0; a < 32; a++) wv[a] = (uint32_t)p[a * 192] | ((uint32_t)p[6144 + a * 192] << 16);
        asm volatile("bar.sync 1, 128;" ::: "memory");
#pragma unroll
        for (int a = 0; a < 8; a++) *(uint4*)(smem + OFF_WRAW + (a * 128 + t) * 16) = make_uint4(wv[4 * a], wv[4 * a + 1], wv[4 * a + 2], wv[4 * a + 3]);
      }
      if (t == 0) PROF_EV(11);
      mbar_wait(bars + 8 * B_X1, 0);
      float2 v[32];
      probe_tag(g_X1p + (size_t)(kg * 8 + tn) * 2048 + lane * 64 + ((lane + w) & 1) * 32 + w * 8, tag);
      if (t == 0) PROF_EV(22);
      load32_tagged(v, (const float2*)g_X1p + (size_t)(kg * 8 + tn) * 2048 + ((t >> 3) & 1) * 32 + w * 8 + (t & 7), 64, tag);
#pragma unroll
      for (int a = 0; a < 32; a++) {
        const uint32_t u = __float_as_uint((t & 16) ? v[a].y : v[a].x);
        v[a] = make_float2(bf_lo(u), bf_hi(u));
      }
      if (t == 0) PROF_EV(12);
      dft<-1, 32, 0, 1>(v);
      float2 y[32];
#pragma unroll
      for (int a4 = 0; a4 < 8; a4++) {
        const uint4 ww = *(const uint4*)(smem + OFF_WRAW + (a4 * 128 + t) * 16);
        const uint32_t wq[4] = {ww.x, ww.y, ww.z, ww.w};
#pragma unroll
        for (int e = 0; e < 4; e++) {
          const float2 z = v[brev(4 * a4 + e, 5)];
          const float wr = bf_lo(wq[e]), wi = bf_hi(wq[e]);
          y[4 * a4 + e] = make_float2(fmaf(z.x, wr, -z.y * wi), fmaf(z.x, wi, z.y * wr));
        }
      }
      dft<1, 32, 0, 1>(y);
      if (t == 0) PROF_EV(16);
      if (k != 0) {
        uint2* dst = g_T + (size_t)j * 32768 + (kg & 1) * 1024 + j1 * 16 + (t & 15);
#pragma unroll
        for (int a = 0; a < 16; a++) {
          const float2 u0 = y[brev(2 * a, 5)], u1 = y[brev(2 * a + 1, 5)];
          st_u2(dst + a * 2048, (pack_bf16(u0.x * scale, u0.y * scale) & ~1u) | tag, pack_bf16(u1.x * scale, u1.y * scale));
        }
      }
      if (t == 0) PROF_EV(17);
      {
        const uint4* src = (const uint4*)(g_T + (size_t)(j * 16 + rb) * 2048) + t;
        uint4 u[8];
        probe_tag(src - lane + (lane >> 2) * 128 + (lane & 3) * 8, tag);
        if (t == 0) PROF_EV(23);
        const uint32_t t0 = (uint32_t)clock();
        for (;;) {
          uint32_t bad = 0;
#pragma unroll
          for (int a = 0; a < 8; a++) u[a] = ld_x4(src + a * 128);
#pragma unroll
          for (int a = 0; a < 8; a++) bad |= (u[a].x ^ tag) | (u[a].z ^ tag);
          if (!__any_sync(0xffffffffu, bad & 1)) break;
          spin_guard(t0);
        }
        const int r = t >> 3, c = t & 7;
#pragma unroll
        for (int a = 0; a < 8; a++) {
          const uint32_t dst = sb + OFF_T + (16 * (a & 3) + r) * 128 + ((((a >> 2) * 4 + (c >> 1)) ^ (r & 7)) << 4) + (c & 1) * 8;
          asm volatile("st.shared.v2.u32 [%0], {%1,%2};" ::"r"(dst), "r"(u[a].x & ~1u), "r"(u[a].z & ~1u) : "memory");
          asm volatile("st.shared.v2.u32 [%0], {%1,%2};" ::"r"(dst + 8192), "r"(u[a].y), "r"(u[a].w) : "memory");
        }
        asm volatile("fence.proxy.async.shared::cta;" ::: "memory");
        __syncwarp();
        if (lane == 0) mbar_arrive(bars + 8 * B_T);
        if (t == 0) PROF_EV(13);
      }
    } else if (w == 0) {
      const uint32_t tag = (ep + 1) & 1;
      const int c = lane >> 4, j1 = 16 * (blockIdx.x - 128) + (lane & 15);
      float2* wf = (float2*)smem;
      float2 v[32];
      probe_tag(g_Wh + 16 * (blockIdx.x - 128) + 64 * lane, tag);
      load32_tagged(v, g_Wh + c * 2048 + j1, 64, tag);
#pragma unroll
      for (int a = 0; a < 32; a++) wf[a * 32 + lane] = v[a];
      if (t == 0) PROF_EV(11);
      probe_tag(g_X1s + 2048 + 16 * (blockIdx.x - 128) + 15 + 64 * lane, tag);
      load32_tagged(v, g_X1s + c * 2048 + j1, 64, tag);
      if (t == 0) PROF_EV(12);
      dft<-1, 32, 0, 1>(v);
      float2 y[32];
#pragma unroll
      for (int a = 0; a < 32; a++) {
        const float2 z = v[brev(a, 5)], wv = wf[a * 32 + lane];
        y[a] = make_float2(fmaf(z.x, wv.x, -z.y * wv.y), fmaf(z.x, wv.y, z.y * wv.x));
      }
      dft<1, 32, 0, 1>(y);
      if (t == 0) PROF_EV(16);
#pragma unroll
      for (int a = 0; a < 8; a++) {
        uint32_t pk[2];
#pragma unroll
        for (int e = 0; e < 2; e++) {
          const float2 u0 = y[brev(4 * a + e, 5)], u1 = y[brev(4 * a + 2 + e, 5)];
          const float2 keep = c ? u1 : u0, give = c ? u0 : u1;
          const float ox = __shfl_xor_sync(0xffffffffu, give.x, 16), oy = __shfl_xor_sync(0xffffffffu, give.y, 16);
          pk[e] = pack_bf16((keep.x + ox) * (0.5f * scale), (keep.y + oy) * (0.5f * scale));
        }
        st_u2(g_T + (2 * a + c) * 2048 + j1 * 16, (pk[0] & ~1u) | tag, pk[1]);
      }
      if (t == 0) { g_epoch[blockIdx.x * 8] = ep + 1; PROF_EV(13); }
    }
  } else {
    asm volatile("setmaxnreg.inc.sync.aligned.u32 200;");
    if (!helper) {
      const int wg = warp >> 2, w = warp & 3, g = lane >> 2, q = lane & 3;
      const bool elect = (tid & 127) == 0;
      const uint32_t ep = ld_x1(&g_epoch[blockIdx.x * 8]);
      float c1[64], cA[64], c2[64], ci[64], ct[64];
      const int zero = blockIdx.x >> 16;
      uint32_t h[56], yf[16];
      const uint32_t d0 = (sb & 0x3FFFF) >> 4;
      const uint32_t dK = d0 | (1u << 16), dN = d0 | (512u << 16), dM = d0 | (256u << 16);
      const uint32_t dX = dK + wg * 512;
      constexpr uint32_t RING = OFF_RING >> 4;
      auto waitA = [&](int n) { mbar_wait(bars + 8 * (B_FA + (n & 3)), (n >> 2) & 1); };
      auto freeA = [&](int n) { if (elect) mbar_arrive(bars + 8 * (B_EA + (n & 3))); };

      auto c1_step = [&](auto first, int kb) {
        mbar_wait(bars + 8 * (B_FX + kb), 0); waitA(kb);
        wg_fence();
        const uint32_t dx = dX + kb * 1024, df = dK + RING + (kb & 3) * 1024, dm = dM + RING + 512 + (kb & 3) * 1024;
        mma_ss64<0, 0, decltype(first)::value>(c1, df, dx);
        mma_ss64<32, 1, decltype(first)::value, H64>(c1, dx, dm);
#pragma unroll
        for (int k = 1; k < 4; k++) {
          mma_ss64<0, 0, 1>(c1, df + k * 2, dx + k * 2);
          mma_ss64<32, 1, 1, H64>(c1, dx + k * 2, dm + k * 64);
        }
        wg_commit();
      };
      c1_step(IC<0>(), 0);
      if (tid == 0) PROF_EV(1);
#pragma unroll 1
      for (int kb = 1; kb < 8; kb++) { c1_step(IC<1>(), kb); wg_wait<1>(); freeA(kb - 1); }
      auto ffn_step = [&](auto first, float (&acc)[64], int n, int kb) {
        waitA(n);
        wg_fence();
        const uint32_t dx = dX + kb * 1024, db = dN + RING + (n & 3) * 1024;
        mma_ss128<0, 1, decltype(first)::value>(acc, dx, db, zero);
#pragma unroll
        for (int k = 1; k < 4; k++) mma_ss128<0, 1, 1>(acc, dx + k * 2, db + k * 128);
        wg_commit();
        wg_wait<1>();
      };
      const uint32_t tag = (ep + 1) & 1;
      const float* gp = g_gate + rb * 128 + wg * 64 + w * 16 + g;
      uint32_t gb0 = ld_x1(gp), gb1 = ld_x1(gp + 8);
      ffn_step(IC<0>(), c2, 8, 0);
      freeA(7);
      fence_regs<0, 64>(c1);
      if (tid == 0) PROF_EV(2);
#pragma unroll
      for (int i = 0; i < 16; i++) yf[i] = pack_pin(c1[2 * i], c1[2 * i + 1]);
      {
        const uint32_t t0 = (uint32_t)clock();
        while (((gb0 ^ tag) | (gb1 ^ tag)) & 1) { gb0 = ld_x1(gp); gb1 = ld_x1(gp + 8); spin_guard(t0); }
        __syncwarp();
      }
      if (tid == 0) PROF_EV(10);
      const float g0 = __uint_as_float(gb0 & ~1u), g1 = __uint_as_float(gb1 & ~1u);
      const float o0 = 1.0f - g0, o1 = 1.0f - g1;
#pragma unroll
      for (int i = 0; i < 8; i++) {
        const float o = (i & 1) ? o1 : o0;
        h[48 + i] = pack_pin(fmaxf(c1[32 + 2 * i], 0.f) * c1[48 + 2 * i] * o, fmaxf(c1[33 + 2 * i], 0.f) * c1[49 + 2 * i] * o);
      }
      {
        waitA(9); waitA(10);
        const uint32_t de = dN + RING + (1 + wg) * 1024;
        wg_fence();
        mma_rs128<0, 1, 0>(cA, yf[0], yf[1], yf[2], yf[3], de);
#pragma unroll
        for (int k = 1; k < 4; k++) mma_rs128<0, 1, 1>(cA, yf[4 * k], yf[4 * k + 1], yf[4 * k + 2], yf[4 * k + 3], de + k * 128);
        wg_commit();
        wg_wait<1>();
        freeA(8);
        ffn_step(IC<1>(), c2, 11, 1);
        freeA(9); freeA(10);
        fence_regs<0, 64>(cA);
        if (tid == 0) PROF_EV(19);
        const int s0 = 2 * rb + wg;
        uint2* dst = g_X1p + ((size_t)((2 * j + (w >> 1)) * 8) * 32 + s0) * 64 + (w & 1) * 32 + q * 8 + g;
#pragma unroll
        for (int n = 0; n < 8; n++)
          st_u2(dst + n * 2048, (pack_bf16(cA[4 * n] - cA[34 + 4 * n], cA[32 + 4 * n] + cA[4 * n + 2]) & ~1u) | tag,
                pack_bf16(cA[4 * n + 1] - cA[35 + 4 * n], cA[33 + 4 * n] + cA[4 * n + 3]));
        if (j == 0 && w == 0 && g == 0) {
#pragma unroll
          for (int n = 0; n < 8; n++) {
#pragma unroll
            for (int e = 0; e < 2; e++) {
              st_x2(g_X1s + s0 * 64 + 8 * n + 2 * q + e, tagf(cA[4 * n + e], tag), cA[32 + 4 * n + e]);
              st_x2(g_X1s + (32 + s0) * 64 + 8 * n + 2 * q + e, tagf(cA[4 * n + 2 + e], tag), cA[34 + 4 * n + e]);
            }
          }
        }
        __syncwarp();
        if (lane == 0) mbar_arrive(bars + 8 * B_X1);
        if (tid == 0) PROF_EV(3);
      }
      auto glu = [&](float (&acc)[64], int ho) {
#pragma unroll
        for (int i = 0; i < 16; i++) {
          const float o = (i & 1) ? o1 : o0;
          h[ho + i] = pack_pin(fmaxf(acc[2 * i], 0.f) * acc[32 + 2 * i] * o, fmaxf(acc[2 * i + 1], 0.f) * acc[33 + 2 * i] * o);
        }
      };
#pragma unroll 1
      for (int kb = 2; kb < 8; kb++) { ffn_step(IC<1>(), c2, 10 + kb, kb); freeA(9 + kb); }
      ffn_step(IC<2>(), cA, 18, 0); freeA(17);
      fence_regs<0, 64>(c2);
      if (tid == 0) PROF_EV(4);
      glu(c2, 0);
#pragma unroll 1
      for (int kb = 1; kb < 8; kb++) { ffn_step(IC<1>(), cA, 18 + kb, kb); freeA(17 + kb); }
      ffn_step(IC<2>(), c2, 26, 0); freeA(25);
      fence_regs<0, 64>(cA);
      if (tid == 0) PROF_EV(5);
      glu(cA, 16);
#pragma unroll 1
      for (int kb = 1; kb < 8; kb++) {
        ffn_step(IC<1>(), c2, 26 + kb, kb); freeA(25 + kb);
        if (elect && kb >= 3 && (kb & 1)) mbar_arrive(bars + 8 * (B_ET + ((kb - 3) >> 1)));
      }
      wg_wait<0>();
      if (elect) mbar_arrive(bars + 8 * (B_ET + 3));
      fence_regs<0, 64>(c2);
      glu(c2, 32);
      waitA(34 + wg);
      if (tid == 0) PROF_EV(6);
      mbar_wait(bars + 8 * B_T, 0);
      if (tid == 0) PROF_EV(7);
      wg_fence();
      {
        const uint32_t dt = dN + (OFF_T >> 4) + wg * 512, de = dK + RING + (2 + wg) * 1024;
        mma_ss64<0, 1, 0>(ci, de, dt);
        mma_ss64<32, 1, 0>(ci, de + 512, dt);
#pragma unroll
        for (int k = 1; k < 4; k++) {
          mma_ss64<0, 1, 1>(ci, de + k * 2, dt + k * 128);
          mma_ss64<32, 1, 1>(ci, de + (512 + k * 2), dt + k * 128);
        }
      }
      wg_commit();

      auto head = [&](auto off, int t) {
        constexpr int O = decltype(off)::value;
        mbar_wait(bars + 8 * (B_FT + (t & 3)), t >> 2);
        const uint32_t db = dN + (t & 3) * (TB >> 4);
        wg_fence();
        mma_rs64<O, 1, 0>(ct, h[0], h[1], h[2], h[3], db);
#pragma unroll
        for (int k = 1; k < 6; k++) mma_rs64<O, 1, 1>(ct, h[4 * k], h[4 * k + 1], h[4 * k + 2], h[4 * k + 3], db + k * 128);
        wg_commit();
        wg_wait<1>();
      };
      auto rest = [&](auto off, int t) {
        constexpr int O = decltype(off)::value;
        const uint32_t db = dN + (t & 3) * (TB >> 4);
        wg_fence();
#pragma unroll
        for (int k = 6; k < 14; k++) mma_rs64<O, 1, 1>(ct, h[4 * k], h[4 * k + 1], h[4 * k + 2], h[4 * k + 3], db + k * 128);
#pragma unroll
        for (int k = 0; k < 4; k++) mma_rs64<O, 1, 1>(ct, yf[4 * k], yf[4 * k + 1], yf[4 * k + 2], yf[4 * k + 3], db + (14 + k) * 128);
        wg_commit();
      };
      auto freeT = [&](int t) { if (elect) mbar_arrive(bars + 8 * (B_ET + t)); };
      const uint32_t peerZ = mapa(sb + OFF_Z + tid * 16, rank ^ 1), peerB = mapa(bars + 8 * B_Z, rank ^ 1);
      auto send_peer = [&](auto off, int z) {
        constexpr int O = decltype(off)::value;
        fence_regs<O, 32>(ct);
#pragma unroll
        for (int i = 0; i < 4; i++)
          asm volatile("st.async.weak.shared::cluster.mbarrier::complete_tx::bytes.v4.b32 [%0], {%1,%2,%3,%4}, [%5];" ::"r"(peerZ + z * U + i * 4096),
                       "r"(pack_bf16(ct[O + 8 * i], ct[O + 8 * i + 1])), "r"(pack_bf16(ct[O + 8 * i + 2], ct[O + 8 * i + 3])),
                       "r"(pack_bf16(ct[O + 8 * i + 4], ct[O + 8 * i + 5])), "r"(pack_bf16(ct[O + 8 * i + 6], ct[O + 8 * i + 7])), "r"(peerB + 8 * z) : "memory");
      };
      auto send_grid = [&](auto off, int z) {
        constexpr int O = decltype(off)::value;
        fence_regs<O, 32>(ct);
        mbar_wait(bars + 8 * (B_Z + z), 0);
        uint4* dst = g_part + (size_t)((rb * 8 + 2 * ((q4 + z + 1) & 3) + rank) * 3 + z) * 1024 + tid;
#pragma unroll
        for (int i = 0; i < 4; i++) {
          const uint4 p = *(const uint4*)(smem + OFF_Z + z * U + i * 4096 + tid * 16);
          st_x4(dst + i * 256, (pack_bf16(ct[O + 8 * i] + bf_lo(p.x), ct[O + 8 * i + 1] + bf_hi(p.x)) & ~1u) | tag,
                pack_bf16(ct[O + 8 * i + 2] + bf_lo(p.y), ct[O + 8 * i + 3] + bf_hi(p.y)),
                pack_bf16(ct[O + 8 * i + 4] + bf_lo(p.z), ct[O + 8 * i + 5] + bf_hi(p.z)),
                pack_bf16(ct[O + 8 * i + 6] + bf_lo(p.w), ct[O + 8 * i + 7] + bf_hi(p.w)));
        }
      };
      asm volatile("barrier.cluster.wait.aligned;" ::: "memory");
      head(IC<0>(), 0);
      if (elect) asm volatile("mbarrier.arrive.shared::cluster.b64 _, [%0];" ::"r"(mapa(bars + 8 * B_RDY, rank ^ 1)) : "memory");
      fence_regs<0, 64>(ci);
#pragma unroll
      for (int i = 0; i < 16; i++) {
        const float gg = (i & 1) ? g1 : g0;
        yf[i] = pack_pin((ci[2 * i] + ci[33 + 2 * i]) * gg, (ci[2 * i + 1] - ci[32 + 2 * i]) * gg);
      }
      rest(IC<0>(), 0);
      if (tid == 0) PROF_EV(8);
      head(IC<32>(), 1); freeT(0); mbar_wait(bars + 8 * B_RDY, 0); send_peer(IC<0>(), 0); rest(IC<32>(), 1);
      head(IC<0>(), 2); freeT(1); send_peer(IC<32>(), 1); rest(IC<0>(), 2);
      head(IC<32>(), 3); freeT(2); send_peer(IC<0>(), 2); rest(IC<32>(), 3);
      head(IC<0>(), 4); freeT(3); send_grid(IC<32>(), 0); rest(IC<0>(), 4);
      head(IC<32>(), 5); send_grid(IC<0>(), 1); rest(IC<32>(), 5);
      head(IC<0>(), 6); send_grid(IC<32>(), 2); rest(IC<0>(), 6);
      head(IC<32>(), 7); send_peer(IC<0>(), 3); rest(IC<32>(), 7);
      if (tid == 0) PROF_EV(9);
      {
        const uint4* src = g_part + (size_t)(rb * 8 + j) * 3 * 1024 + tid;
        uint4 pv[12];
        const uint32_t t0 = (uint32_t)clock();
        for (;;) {
          uint32_t bad = 0;
#pragma unroll
          for (int i = 0; i < 12; i++) pv[i] = ld_x4(src + i * 256);
#pragma unroll
          for (int i = 0; i < 12; i++) bad |= pv[i].x ^ tag;
          if (!__any_sync(0xffffffffu, bad & 1)) break;
          probe_tag(src - lane + ((lane & 3) == 3 ? 0 : (lane & 3)) * 1024 + 768, tag);
          spin_guard(t0);
        }
        if (tid == 0) PROF_EV(14);
        float sum[32];
#pragma unroll
        for (int i = 0; i < 4; i++) {
          const uint32_t a[4] = {pv[i].x & ~1u, pv[i].y, pv[i].z, pv[i].w}, b[4] = {pv[4 + i].x & ~1u, pv[4 + i].y, pv[4 + i].z, pv[4 + i].w},
                         c[4] = {pv[8 + i].x & ~1u, pv[8 + i].y, pv[8 + i].z, pv[8 + i].w};
#pragma unroll
          for (int e = 0; e < 4; e++) {
            sum[8 * i + 2 * e] = bf_lo(a[e]) + bf_lo(b[e]) + bf_lo(c[e]);
            sum[8 * i + 2 * e + 1] = bf_hi(a[e]) + bf_hi(b[e]) + bf_hi(c[e]);
          }
        }
        mbar_wait(bars + 8 * (B_Z + 3), 0);
#pragma unroll
        for (int i = 0; i < 4; i++) {
          const uint4 p = *(const uint4*)(smem + OFF_Z + 3 * U + i * 4096 + tid * 16);
          const uint32_t a[4] = {p.x, p.y, p.z, p.w};
#pragma unroll
          for (int e = 0; e < 4; e++) { sum[8 * i + 2 * e] += bf_lo(a[e]); sum[8 * i + 2 * e + 1] += bf_hi(a[e]); }
        }
        wg_wait<0>();
        fence_regs<32, 32>(ct);
#pragma unroll
        for (int i = 0; i < 32; i++) sum[i] += ct[32 + i];
        const uint32_t stg = sb + OFF_T + warp * 2048;
        const int mr = (lane & 7) + ((lane >> 3) & 1) * 8, mc = lane >> 4;
#pragma unroll
        for (int i = 0; i < 4; i++) {
          const uint32_t a = stg + mr * 128 + (((2 * i + mc) ^ (mr & 7)) << 4);
          asm volatile("stmatrix.sync.aligned.m8n8.x4.shared.b16 [%0], {%1,%2,%3,%4};" ::"r"(a), "r"(pack_bf16(sum[8 * i], sum[8 * i + 1])),
                       "r"(pack_bf16(sum[8 * i + 2], sum[8 * i + 3])), "r"(pack_bf16(sum[8 * i + 4], sum[8 * i + 5])),
                       "r"(pack_bf16(sum[8 * i + 6], sum[8 * i + 7])) : "memory");
        }
        __syncwarp();
#pragma unroll
        for (int i = 0; i < 4; i++) {
          const int r = 4 * i + (lane >> 3), c = lane & 7;
          const uint4 v = *(const uint4*)(smem + OFF_T + warp * 2048 + r * 128 + ((c ^ (r & 7)) << 4));
          *(uint4*)(out + (size_t)(2 * rb + wg + 32 * (16 * w + r)) * 512 + 64 * j + 8 * c) = v;
        }
      }
      if (tid == 0) { g_epoch[blockIdx.x * 8] = ep + 1; PROF_EV(15); PROF_CK(41); }
    }
  }
}

typedef CUresult (*EncodeFn)(CUtensorMap*, CUtensorMapDataType, cuuint32_t, void*, const cuuint64_t*, const cuuint64_t*, const cuuint32_t*,
                             const cuuint32_t*, CUtensorMapInterleave, CUtensorMapSwizzle, CUtensorMapL2promotion, CUtensorMapFloatOOBfill);

static void encode(EncodeFn f, CUtensorMap* m, const void* base, int rank, const cuuint64_t* dims, const cuuint64_t* strides, const cuuint32_t* box,
                   CUtensorMapSwizzle sw) {
  cuuint32_t es[5] = {1, 1, 1, 1, 1};
  f(m, CU_TENSOR_MAP_DATA_TYPE_BFLOAT16, rank, (void*)base, dims, strides, box, es, CU_TENSOR_MAP_INTERLEAVE_NONE, sw,
    CU_TENSOR_MAP_L2_PROMOTION_L2_128B, CU_TENSOR_MAP_FLOAT_OOB_FILL_NONE);
}

extern "C" void kernel_launch(void* const* d_in, const int* in_sizes, int n_in, void* d_out, int out_size) {
  (void)in_sizes; (void)n_in; (void)out_size;
  const __nv_bfloat16* x = (const __nv_bfloat16*)d_in[0];
  const __nv_bfloat16* w_r = (const __nv_bfloat16*)d_in[1];
  const __nv_bfloat16* w_i = (const __nv_bfloat16*)d_in[2];
  const __nv_bfloat16* Wg = (const __nv_bfloat16*)d_in[4];
  const __nv_bfloat16* Wu = (const __nv_bfloat16*)d_in[5];
  const __nv_bfloat16* Wd = (const __nv_bfloat16*)d_in[6];
  const __nv_bfloat16* gw = (const __nv_bfloat16*)d_in[7];

  void* fp = nullptr; cudaDriverEntryPointQueryResult qr;
  cudaGetDriverEntryPoint("cuTensorMapEncodeTiled", &fp, cudaEnableDefault, &qr);
  EncodeFn enc = (EncodeFn)fp;
  void *pFT, *pET;
  cudaGetSymbolAddress(&pFT, g_FT); cudaGetSymbolAddress(&pET, g_ET);

  Maps mp;
  const CUtensorMapSwizzle S128 = CU_TENSOR_MAP_SWIZZLE_128B, S64 = CU_TENSOR_MAP_SWIZZLE_64B;
  { cuuint64_t d[3] = {512, 64, 32}, s[2] = {32768, 1024}; cuuint32_t b[3] = {64, 64, 2}; encode(enc, &mp.x, x, 3, d, s, b, S128); }
  { cuuint64_t d[2] = {512, 512}, s[1] = {1024}; cuuint32_t b[2] = {64, 64}; encode(enc, &mp.ft, pFT, 2, d, s, b, S128); }
  { cuuint64_t d[4] = {512, 2, 8, 32}, s[3] = {8192, 1024, 16384}; cuuint32_t b[4] = {64, 2, 8, 4}; encode(enc, &mp.fg, pFT, 4, d, s, b, S128); }
  { cuuint64_t d[4] = {64, 64, 2, 32}, s[3] = {8192, 128, 256}; cuuint32_t b[4] = {64, 64, 2, 1}; encode(enc, &mp.e, pET, 4, d, s, b, S128); }
  { cuuint64_t d[2] = {1792, 512}, s[1] = {3584}; cuuint32_t b[2] = {64, 64}, b2[2] = {32, 64};
    encode(enc, &mp.g64, Wg, 2, d, s, b, S128); encode(enc, &mp.u64, Wu, 2, d, s, b, S128);
    encode(enc, &mp.g32, Wg, 2, d, s, b2, S64); encode(enc, &mp.u32, Wu, 2, d, s, b2, S64); }
  { cuuint64_t d[2] = {512, 1792}, s[1] = {1024}; cuuint32_t b[2] = {64, 192}, b2[2] = {64, 32};
    encode(enc, &mp.d192, Wd, 2, d, s, b, S128); encode(enc, &mp.d32, Wd, 2, d, s, b2, S128); }

  { cuuint64_t d[4] = {264, 8, 8, 32}, s[3] = {512, 4112, 32896}; cuuint32_t b[4] = {24, 8, 1, 32};
    encode(enc, &mp.wr, w_r, 4, d, s, b, CU_TENSOR_MAP_SWIZZLE_NONE); encode(enc, &mp.wi, w_i, 4, d, s, b, CU_TENSOR_MAP_SWIZZLE_NONE); }

  cudaFuncSetAttribute(fused_kernel, cudaFuncAttributeMaxDynamicSharedMemorySize, SMEM_BYTES);
  fused_kernel<<<NCTA, 512, SMEM_BYTES>>>(mp, x, w_r, w_i, gw, Wd, (__nv_bfloat16*)d_out);
}
```

```cpp
#include <cuda_runtime.h>
#include <cuda_bf16.h>
#include <cuda.h>
#include <stdint.h>

namespace tbl {
constexpr double PI = 3.14159265358979323846264338327950288;
constexpr double sin_s(double x) { double t = x, s = x; for (int n = 1; n < 12; n++) { t *= -x * x / ((2 * n) * (2 * n + 1)); s += t; } return s; }
constexpr double cos_s(double x) { double t = 1, s = 1; for (int n = 1; n < 12; n++) { t *= -x * x / ((2 * n - 1) * (2 * n)); s += t; } return s; }
constexpr double cos2048(int m) {
  m &= 2047; if (m > 1024) m = 2048 - m;
  bool neg = false; if (m > 512) { m = 1024 - m; neg = true; }
  double v = (m <= 256) ? cos_s(2 * PI * m / 2048) : sin_s(2 * PI * (512 - m) / 2048);
  return neg ? -v : v;
}
constexpr uint16_t to_bf16(double v) {
  if (v == 0) return 0;
  uint16_t s = 0; if (v < 0) { s = 0x8000; v = -v; }
  int e = 0; while (v >= 2) { v /= 2; e++; } while (v < 1) { v *= 2; e--; }
  double m = (v - 1) * 128; int mi = (int)m; double fr = m - mi;
  if (fr > 0.5 || (fr == 0.5 && (mi & 1))) mi++;
  if (mi == 128) { mi = 0; e++; }
  return (uint16_t)(s | ((e + 127) << 7) | mi);
}
struct CosT { uint16_t v[2048]; constexpr CosT() : v() { for (int i = 0; i < 2048; i++) v[i] = to_bf16(cos2048(i)); } };
struct alignas(1024) FT {
  uint16_t v[512 * 512];
  constexpr FT() : v() {
    CosT c;
    for (int r = 0; r < 512; r++) {
      int k = (r >> 4) * 8 + (r & 7), e = (r >> 3) & 1;
      int mul = 4 * k, add = e ? 512 : 0;
      if (k == 0 && e == 1) { mul = 1024; add = 0; }
      for (int d = 0; d < 512; d++) v[r * 512 + d] = c.v[(d * mul + add) & 2047];
    }
  }
};
struct alignas(1024) ET {
  uint16_t v[2048 * 128];
  constexpr ET() : v() {
    CosT c;
    for (int s = 0; s < 2048; s++)
      for (int j = 0; j < 64; j++) { v[s * 128 + j] = c.v[(s * j) & 2047]; v[s * 128 + 64 + j] = c.v[(s * j + 512) & 2047]; }
  }
};
template <int A> struct W32 {
  static constexpr float c = (float)cos2048(A * 64);
  static constexpr float s = (float)cos2048(A * 64 - 512);
};
}

__device__ constexpr tbl::FT g_FT = tbl::FT();
__device__ constexpr tbl::ET g_ET = tbl::ET();

__device__ __align__(1024) uint2 g_X1p[128 * 32 * 64];
__device__ __align__(1024) float2 g_X1s[2 * 32 * 64];
__device__ __align__(1024) uint2 g_T[8 * 16 * 2 * 64 * 16];
__device__ __align__(1024) uint4 g_part[128 * 3 * 1024];
__device__ __align__(16) float g_gate[16 * 128];
__device__ __align__(16) float2 g_Wh[2 * 2048];
__device__ unsigned g_epoch[132 * 8];
__device__ unsigned g_cntX[8 * 32], g_cntT[8 * 32], g_cntP[128 * 32], g_cntW[32];
#define PROF_EV(i) do {} while (0)
#define PROF_CK(i) do {} while (0)

__device__ __forceinline__ uint32_t smem_u32(const void* p) { return (uint32_t)__cvta_generic_to_shared(p); }
__device__ __forceinline__ void mbar_init(uint32_t bar, uint32_t cnt) { asm volatile("mbarrier.init.shared::cta.b64 [%0], %1;" ::"r"(bar), "r"(cnt)); }
__device__ __forceinline__ void mbar_expect_tx(uint32_t bar, uint32_t bytes) { asm volatile("mbarrier.arrive.expect_tx.shared::cta.b64 _, [%0], %1;" ::"r"(bar), "r"(bytes) : "memory"); }
__device__ __forceinline__ void mbar_arrive(uint32_t bar) { asm volatile("mbarrier.arrive.shared::cta.b64 _, [%0];" ::"r"(bar) : "memory"); }
__device__ __forceinline__ bool mbar_try(uint32_t bar, uint32_t parity) {
  uint32_t ok;
  asm volatile("{\n.reg .pred p;\nmbarrier.try_wait.parity.shared::cta.b64 p, [%1], %2;\nselp.u32 %0, 1, 0, p;\n}" : "=r"(ok) : "r"(bar), "r"(parity) : "memory");
  return ok;
}
__device__ __forceinline__ void mbar_wait(uint32_t bar, uint32_t parity) {
  if (mbar_try(bar, parity)) return;
  const uint32_t t0 = (uint32_t)clock();
  while (!mbar_try(bar, parity)) { if ((uint32_t)clock() - t0 > (1u << 30)) __trap(); }
}
__device__ __forceinline__ void spin_guard(uint32_t t0) { if ((uint32_t)clock() - t0 > (1u << 30)) __trap(); }
__device__ __forceinline__ float tagf(float v, uint32_t tag) { return __uint_as_float((__float_as_uint(v) & ~1u) | tag); }
__device__ __forceinline__ float untag(float v) { return __uint_as_float(__float_as_uint(v) & ~1u); }
__device__ __forceinline__ void st_x2(float2* p, float a, float b) { asm volatile("st.relaxed.gpu.global.v2.f32 [%0], {%1,%2};" ::"l"(p), "f"(a), "f"(b) : "memory"); }
__device__ __forceinline__ float2 ld_x2(const float2* p) { float2 v; asm volatile("ld.relaxed.gpu.global.v2.f32 {%0,%1}, [%2];" : "=f"(v.x), "=f"(v.y) : "l"(p) : "memory"); return v; }
__device__ __forceinline__ void st_u2(uint2* p, uint32_t a, uint32_t b) { asm volatile("st.relaxed.gpu.global.v2.u32 [%0], {%1,%2};" ::"l"(p), "r"(a), "r"(b) : "memory"); }
__device__ __forceinline__ void prefetch2d(const CUtensorMap* m, int c0, int c1) { asm volatile("cp.async.bulk.prefetch.tensor.2d.L2.global [%0, {%1, %2}];" ::"l"(m), "r"(c0), "r"(c1) : "memory"); }
__device__ __forceinline__ void prefetch1d(const void* p, uint32_t bytes) { asm volatile("cp.async.bulk.prefetch.L2.global [%0], %1;" ::"l"(p), "r"(bytes) : "memory"); }
__device__ __forceinline__ uint32_t ld_x1(const void* p) { uint32_t v; asm volatile("ld.relaxed.gpu.global.u32 %0, [%1];" : "=r"(v) : "l"(p) : "memory"); return v; }
__device__ __forceinline__ uint4 ld_x4(const void* p) { uint4 v; asm volatile("ld.relaxed.gpu.global.v4.u32 {%0,%1,%2,%3}, [%4];" : "=r"(v.x), "=r"(v.y), "=r"(v.z), "=r"(v.w) : "l"(p) : "memory"); return v; }
__device__ __forceinline__ void st_x4(void* p, uint32_t a, uint32_t b, uint32_t c, uint32_t d) { asm volatile("st.relaxed.gpu.global.v4.u32 [%0], {%1,%2,%3,%4};" ::"l"(p), "r"(a), "r"(b), "r"(c), "r"(d) : "memory"); }
__device__ __forceinline__ uint32_t mapa(uint32_t a, uint32_t cta) { uint32_t r; asm volatile("mapa.shared::cluster.u32 %0, %1, %2;" : "=r"(r) : "r"(a), "r"(cta)); return r; }
__device__ __forceinline__ void hint_add(unsigned* p) { asm volatile("red.relaxed.gpu.global.add.u32 [%0], 1;" ::"l"(p) : "memory"); }
__device__ __forceinline__ void hint_wait(const unsigned* p, unsigned target) {
  const uint32_t t0 = (uint32_t)clock();
  while ((int)(ld_x1(p) - target) < 0) spin_guard(t0);
}
__device__ __forceinline__ void load32_tagged(float2 (&v)[32], const float2* src, int stride, uint32_t tag) {
  const uint32_t t0 = (uint32_t)clock();
  for (;;) {
    uint32_t bad = 0;
#pragma unroll
    for (int a = 0; a < 32; a++) v[a] = ld_x2(src + a * stride);
#pragma unroll
    for (int a = 0; a < 32; a++) bad |= __float_as_uint(v[a].x) ^ tag;
    if (!__any_sync(0xffffffffu, bad & 1)) break;
    spin_guard(t0);
  }
#pragma unroll
  for (int a = 0; a < 32; a++) v[a].x = untag(v[a].x);
}
__device__ __forceinline__ void tma2d(uint32_t dst, const CUtensorMap* m, uint32_t bar, int c0, int c1) {
  asm volatile("cp.async.bulk.tensor.2d.shared::cluster.global.mbarrier::complete_tx::bytes [%0], [%1, {%3, %4}], [%2];" ::"r"(dst), "l"(m), "r"(bar), "r"(c0), "r"(c1) : "memory");
}
__device__ __forceinline__ void tma3d(uint32_t dst, const CUtensorMap* m, uint32_t bar, int c0, int c1, int c2) {
  asm volatile("cp.async.bulk.tensor.3d.shared::cluster.global.mbarrier::complete_tx::bytes [%0], [%1, {%3, %4, %5}], [%2];" ::"r"(dst), "l"(m), "r"(bar), "r"(c0), "r"(c1), "r"(c2) : "memory");
}
__device__ __forceinline__ void tma4d(uint32_t dst, const CUtensorMap* m, uint32_t bar, int c0, int c1, int c2, int c3) {
  asm volatile("cp.async.bulk.tensor.4d.shared::cluster.global.mbarrier::complete_tx::bytes [%0], [%1, {%3, %4, %5, %6}], [%2];" ::"r"(dst), "l"(m), "r"(bar), "r"(c0), "r"(c1), "r"(c2), "r"(c3) : "memory");
}
__device__ __forceinline__ void wg_fence() { asm volatile("wgmma.fence.sync.aligned;" ::: "memory"); }
__device__ __forceinline__ void wg_commit() { asm volatile("wgmma.commit_group.sync.aligned;" ::: "memory"); }
template <int N> __device__ __forceinline__ void wg_wait() { asm volatile("wgmma.wait_group.sync.aligned %0;" ::"n"(N) : "memory"); }
template <int O, int N, int NN> __device__ __forceinline__ void fence_regs(float (&d)[NN]) {
#pragma unroll
  for (int i = 0; i < N; i++) asm volatile("" : "+f"(d[O + i])::"memory");
}
__device__ __forceinline__ uint32_t pack_bf16(float lo, float hi) {
  uint32_t r; asm("cvt.rn.bf16x2.f32 %0, %1, %2;" : "=r"(r) : "f"(hi), "f"(lo)); return r;
}
__device__ __forceinline__ uint32_t pack_pin(float lo, float hi) {
  uint32_t r; asm volatile("cvt.rn.bf16x2.f32 %0, %1, %2;" : "=r"(r) : "f"(hi), "f"(lo) : "memory"); return r;
}
__device__ __forceinline__ float bf_lo(uint32_t u) { return __uint_as_float(u << 16); }
__device__ __forceinline__ float bf_hi(uint32_t u) { return __uint_as_float(u & 0xffff0000u); }

constexpr uint32_t H128 = 0x40000040u;
constexpr uint32_t H64 = 0x80000020u;
template<int O,int TB,int ACC,uint32_t HB = H128,int NN> __device__ __forceinline__ void mma_ss64(float (&d)[NN], uint32_t da, uint32_t db, int sd = 0){
  if constexpr (ACC == 1) asm volatile("{\n.reg .b64 da, db;\nmov.b64 da, {%32, %36};\nmov.b64 db, {%33, %35};\nwgmma.mma_async.sync.aligned.m64n64k16.f32.bf16.bf16 {%0,%1,%2,%3,%4,%5,%6,%7,%8,%9,%10,%11,%12,%13,%14,%15,%16,%17,%18,%19,%20,%21,%22,%23,%24,%25,%26,%27,%28,%29,%30,%31}, da, db, 1, 1, 1, 0, %34;\n}"
   : "+f"(d[O+0]), "+f"(d[O+1]), "+f"(d[O+2]), "+f"(d[O+3]), "+f"(d[O+4]), "+f"(d[O+5]), "+f"(d[O+6]), "+f"(d[O+7]), "+f"(d[O+8]), "+f"(d[O+9]), "+f"(d[O+10]), "+f"(d[O+11]), "+f"(d[O+12]), "+f"(d[O+13]), "+f"(d[O+14]), "+f"(d[O+15]), "+f"(d[O+16]), "+f"(d[O+17]), "+f"(d[O+18]), "+f"(d[O+19]), "+f"(d[O+20]), "+f"(d[O+21]), "+f"(d[O+22]), "+f"(d[O+23]), "+f"(d[O+24]), "+f"(d[O+25]), "+f"(d[O+26]), "+f"(d[O+27]), "+f"(d[O+28]), "+f"(d[O+29]), "+f"(d[O+30]), "+f"(d[O+31])
   : "r"(da), "r"(db), "n"(TB), "n"(HB), "n"(H128));
  else if constexpr (ACC == 0) asm volatile("{\n.reg .b64 da, db;\nmov.b64 da, {%32, %36};\nmov.b64 db, {%33, %35};\nwgmma.mma_async.sync.aligned.m64n64k16.f32.bf16.bf16 {%0,%1,%2,%3,%4,%5,%6,%7,%8,%9,%10,%11,%12,%13,%14,%15,%16,%17,%18,%19,%20,%21,%22,%23,%24,%25,%26,%27,%28,%29,%30,%31}, da, db, 0, 1, 1, 0, %34;\n}"
   : "=f"(d[O+0]), "=f"(d[O+1]), "=f"(d[O+2]), "=f"(d[O+3]), "=f"(d[O+4]), "=f"(d[O+5]), "=f"(d[O+6]), "=f"(d[O+7]), "=f"(d[O+8]), "=f"(d[O+9]), "=f"(d[O+10]), "=f"(d[O+11]), "=f"(d[O+12]), "=f"(d[O+13]), "=f"(d[O+14]), "=f"(d[O+15]), "=f"(d[O+16]), "=f"(d[O+17]), "=f"(d[O+18]), "=f"(d[O+19]), "=f"(d[O+20]), "=f"(d[O+21]), "=f"(d[O+22]), "=f"(d[O+23]), "=f"(d[O+24]), "=f"(d[O+25]), "=f"(d[O+26]), "=f"(d[O+27]), "=f"(d[O+28]), "=f"(d[O+29]), "=f"(d[O+30]), "=f"(d[O+31])
   : "r"(da), "r"(db), "n"(TB), "n"(HB), "n"(H128));
  else asm volatile("{\n.reg .pred p;\n.reg .b64 da, db;\nmov.b64 da, {%32, %36};\nmov.b64 db, {%33, %35};\nsetp.ne.b32 p, %37, 0;\nwgmma.mma_async.sync.aligned.m64n64k16.f32.bf16.bf16 {%0,%1,%2,%3,%4,%5,%6,%7,%8,%9,%10,%11,%12,%13,%14,%15,%16,%17,%18,%19,%20,%21,%22,%23,%24,%25,%26,%27,%28,%29,%30,%31}, da, db, p, 1, 1, 0, %34;\n}"
   : "+f"(d[O+0]), "+f"(d[O+1]), "+f"(d[O+2]), "+f"(d[O+3]), "+f"(d[O+4]), "+f"(d[O+5]), "+f"(d[O+6]), "+f"(d[O+7]), "+f"(d[O+8]), "+f"(d[O+9]), "+f"(d[O+10]), "+f"(d[O+11]), "+f"(d[O+12]), "+f"(d[O+13]), "+f"(d[O+14]), "+f"(d[O+15]), "+f"(d[O+16]), "+f"(d[O+17]), "+f"(d[O+18]), "+f"(d[O+19]), "+f"(d[O+20]), "+f"(d[O+21]), "+f"(d[O+22]), "+f"(d[O+23]), "+f"(d[O+24]), "+f"(d[O+25]), "+f"(d[O+26]), "+f"(d[O+27]), "+f"(d[O+28]), "+f"(d[O+29]), "+f"(d[O+30]), "+f"(d[O+31])
   : "r"(da), "r"(db), "n"(TB), "n"(HB), "n"(H128), "r"(sd));
}
template<int O,int TB,int ACC,uint32_t HB = H128,int NN> __device__ __forceinline__ void mma_rs64(float (&d)[NN], uint32_t a0, uint32_t a1, uint32_t a2, uint32_t a3, uint32_t db, int sd = 0){
  if constexpr (ACC == 1) asm volatile("{\n.reg .b64 db;\nmov.b64 db, {%36, %38};\nwgmma.mma_async.sync.aligned.m64n64k16.f32.bf16.bf16 {%0,%1,%2,%3,%4,%5,%6,%7,%8,%9,%10,%11,%12,%13,%14,%15,%16,%17,%18,%19,%20,%21,%22,%23,%24,%25,%26,%27,%28,%29,%30,%31}, {%32,%33,%34,%35}, db, 1, 1, 1, %37;\n}"
   : "+f"(d[O+0]), "+f"(d[O+1]), "+f"(d[O+2]), "+f"(d[O+3]), "+f"(d[O+4]), "+f"(d[O+5]), "+f"(d[O+6]), "+f"(d[O+7]), "+f"(d[O+8]), "+f"(d[O+9]), "+f"(d[O+10]), "+f"(d[O+11]), "+f"(d[O+12]), "+f"(d[O+13]), "+f"(d[O+14]), "+f"(d[O+15]), "+f"(d[O+16]), "+f"(d[O+17]), "+f"(d[O+18]), "+f"(d[O+19]), "+f"(d[O+20]), "+f"(d[O+21]), "+f"(d[O+22]), "+f"(d[O+23]), "+f"(d[O+24]), "+f"(d[O+25]), "+f"(d[O+26]), "+f"(d[O+27]), "+f"(d[O+28]), "+f"(d[O+29]), "+f"(d[O+30]), "+f"(d[O+31])
   : "r"(a0), "r"(a1), "r"(a2), "r"(a3), "r"(db), "n"(TB), "n"(HB));
  else if constexpr (ACC == 0) asm volatile("{\n.reg .b64 db;\nmov.b64 db, {%36, %38};\nwgmma.mma_async.sync.aligned.m64n64k16.f32.bf16.bf16 {%0,%1,%2,%3,%4,%5,%6,%7,%8,%9,%10,%11,%12,%13,%14,%15,%16,%17,%18,%19,%20,%21,%22,%23,%24,%25,%26,%27,%28,%29,%30,%31}, {%32,%33,%34,%35}, db, 0, 1, 1, %37;\n}"
   : "=f"(d[O+0]), "=f"(d[O+1]), "=f"(d[O+2]), "=f"(d[O+3]), "=f"(d[O+4]), "=f"(d[O+5]), "=f"(d[O+6]), "=f"(d[O+7]), "=f"(d[O+8]), "=f"(d[O+9]), "=f"(d[O+10]), "=f"(d[O+11]), "=f"(d[O+12]), "=f"(d[O+13]), "=f"(d[O+14]), "=f"(d[O+15]), "=f"(d[O+16]), "=f"(d[O+17]), "=f"(d[O+18]), "=f"(d[O+19]), "=f"(d[O+20]), "=f"(d[O+21]), "=f"(d[O+22]), "=f"(d[O+23]), "=f"(d[O+24]), "=f"(d[O+25]), "=f"(d[O+26]), "=f"(d[O+27]), "=f"(d[O+28]), "=f"(d[O+29]), "=f"(d[O+30]), "=f"(d[O+31])
   : "r"(a0), "r"(a1), "r"(a2), "r"(a3), "r"(db), "n"(TB), "n"(HB));
  else asm volatile("{\n.reg .pred p;\n.reg .b64 db;\nmov.b64 db, {%36, %38};\nsetp.ne.b32 p, %39, 0;\nwgmma.mma_async.sync.aligned.m64n64k16.f32.bf16.bf16 {%0,%1,%2,%3,%4,%5,%6,%7,%8,%9,%10,%11,%12,%13,%14,%15,%16,%17,%18,%19,%20,%21,%22,%23,%24,%25,%26,%27,%28,%29,%30,%31}, {%32,%33,%34,%35}, db, p, 1, 1, %37;\n}"
   : "+f"(d[O+0]), "+f"(d[O+1]), "+f"(d[O+2]), "+f"(d[O+3]), "+f"(d[O+4]), "+f"(d[O+5]), "+f"(d[O+6]), "+f"(d[O+7]), "+f"(d[O+8]), "+f"(d[O+9]), "+f"(d[O+10]), "+f"(d[O+11]), "+f"(d[O+12]), "+f"(d[O+13]), "+f"(d[O+14]), "+f"(d[O+15]), "+f"(d[O+16]), "+f"(d[O+17]), "+f"(d[O+18]), "+f"(d[O+19]), "+f"(d[O+20]), "+f"(d[O+21]), "+f"(d[O+22]), "+f"(d[O+23]), "+f"(d[O+24]), "+f"(d[O+25]), "+f"(d[O+26]), "+f"(d[O+27]), "+f"(d[O+28]), "+f"(d[O+29]), "+f"(d[O+30]), "+f"(d[O+31])
   : "r"(a0), "r"(a1), "r"(a2), "r"(a3), "r"(db), "n"(TB), "n"(HB), "r"(sd));
}
template<int O,int TB,int ACC,uint32_t HB = H128,int NN> __device__ __forceinline__ void mma_ss128(float (&d)[NN], uint32_t da, uint32_t db, int sd = 0){
  if constexpr (ACC == 1) asm volatile("{\n.reg .b64 da, db;\nmov.b64 da, {%64, %68};\nmov.b64 db, {%65, %67};\nwgmma.mma_async.sync.aligned.m64n128k16.f32.bf16.bf16 {%0,%1,%2,%3,%4,%5,%6,%7,%8,%9,%10,%11,%12,%13,%14,%15,%16,%17,%18,%19,%20,%21,%22,%23,%24,%25,%26,%27,%28,%29,%30,%31,%32,%33,%34,%35,%36,%37,%38,%39,%40,%41,%42,%43,%44,%45,%46,%47,%48,%49,%50,%51,%52,%53,%54,%55,%56,%57,%58,%59,%60,%61,%62,%63}, da, db, 1, 1, 1, 0, %66;\n}"
   : "+f"(d[O+0]), "+f"(d[O+1]), "+f"(d[O+2]), "+f"(d[O+3]), "+f"(d[O+4]), "+f"(d[O+5]), "+f"(d[O+6]), "+f"(d[O+7]), "+f"(d[O+8]), "+f"(d[O+9]), "+f"(d[O+10]), "+f"(d[O+11]), "+f"(d[O+12]), "+f"(d[O+13]), "+f"(d[O+14]), "+f"(d[O+15]), "+f"(d[O+16]), "+f"(d[O+17]), "+f"(d[O+18]), "+f"(d[O+19]), "+f"(d[O+20]), "+f"(d[O+21]), "+f"(d[O+22]), "+f"(d[O+23]), "+f"(d[O+24]), "+f"(d[O+25]), "+f"(d[O+26]), "+f"(d[O+27]), "+f"(d[O+28]), "+f"(d[O+29]), "+f"(d[O+30]), "+f"(d[O+31]), "+f"(d[O+32]), "+f"(d[O+33]), "+f"(d[O+34]), "+f"(d[O+35]), "+f"(d[O+36]), "+f"(d[O+37]), "+f"(d[O+38]), "+f"(d[O+39]), "+f"(d[O+40]), "+f"(d[O+41]), "+f"(d[O+42]), "+f"(d[O+43]), "+f"(d[O+44]), "+f"(d[O+45]), "+f"(d[O+46]), "+f"(d[O+47]), "+f"(d[O+48]), "+f"(d[O+49]), "+f"(d[O+50]), "+f"(d[O+51]), "+f"(d[O+52]), "+f"(d[O+53]), "+f"(d[O+54]), "+f"(d[O+55]), "+f"(d[O+56]), "+f"(d[O+57]), "+f"(d[O+58]), "+f"(d[O+59]), "+f"(d[O+60]), "+f"(d[O+61]), "+f"(d[O+62]), "+f"(d[O+63])
   : "r"(da), "r"(db), "n"(TB), "n"(HB), "n"(H128));
  else if constexpr (ACC == 0) asm volatile("{\n.reg .b64 da, db;\nmov.b64 da, {%64, %68};\nmov.b64 db, {%65, %67};\nwgmma.mma_async.sync.aligned.m64n128k16.f32.bf16.bf16 {%0,%1,%2,%3,%4,%5,%6,%7,%8,%9,%10,%11,%12,%13,%14,%15,%16,%17,%18,%19,%20,%21,%22,%23,%24,%25,%26,%27,%28,%29,%30,%31,%32,%33,%34,%35,%36,%37,%38,%39,%40,%41,%42,%43,%44,%45,%46,%47,%48,%49,%50,%51,%52,%53,%54,%55,%56,%57,%58,%59,%60,%61,%62,%63}, da, db, 0, 1, 1, 0, %66;\n}"
   : "=f"(d[O+0]), "=f"(d[O+1]), "=f"(d[O+2]), "=f"(d[O+3]), "=f"(d[O+4]), "=f"(d[O+5]), "=f"(d[O+6]), "=f"(d[O+7]), "=f"(d[O+8]), "=f"(d[O+9]), "=f"(d[O+10]), "=f"(d[O+11]), "=f"(d[O+12]), "=f"(d[O+13]), "=f"(d[O+14]), "=f"(d[O+15]), "=f"(d[O+16]), "=f"(d[O+17]), "=f"(d[O+18]), "=f"(d[O+19]), "=f"(d[O+20]), "=f"(d[O+21]), "=f"(d[O+22]), "=f"(d[O+23]), "=f"(d[O+24]), "=f"(d[O+25]), "=f"(d[O+26]), "=f"(d[O+27]), "=f"(d[O+28]), "=f"(d[O+29]), "=f"(d[O+30]), "=f"(d[O+31]), "=f"(d[O+32]), "=f"(d[O+33]), "=f"(d[O+34]), "=f"(d[O+35]), "=f"(d[O+36]), "=f"(d[O+37]), "=f"(d[O+38]), "=f"(d[O+39]), "=f"(d[O+40]), "=f"(d[O+41]), "=f"(d[O+42]), "=f"(d[O+43]), "=f"(d[O+44]), "=f"(d[O+45]), "=f"(d[O+46]), "=f"(d[O+47]), "=f"(d[O+48]), "=f"(d[O+49]), "=f"(d[O+50]), "=f"(d[O+51]), "=f"(d[O+52]), "=f"(d[O+53]), "=f"(d[O+54]), "=f"(d[O+55]), "=f"(d[O+56]), "=f"(d[O+57]), "=f"(d[O+58]), "=f"(d[O+59]), "=f"(d[O+60]), "=f"(d[O+61]), "=f"(d[O+62]), "=f"(d[O+63])
   : "r"(da), "r"(db), "n"(TB), "n"(HB), "n"(H128));
  else asm volatile("{\n.reg .pred p;\n.reg .b64 da, db;\nmov.b64 da, {%64, %68};\nmov.b64 db, {%65, %67};\nsetp.ne.b32 p, %69, 0;\nwgmma.mma_async.sync.aligned.m64n128k16.f32.bf16.bf16 {%0,%1,%2,%3,%4,%5,%6,%7,%8,%9,%10,%11,%12,%13,%14,%15,%16,%17,%18,%19,%20,%21,%22,%23,%24,%25,%26,%27,%28,%29,%30,%31,%32,%33,%34,%35,%36,%37,%38,%39,%40,%41,%42,%43,%44,%45,%46,%47,%48,%49,%50,%51,%52,%53,%54,%55,%56,%57,%58,%59,%60,%61,%62,%63}, da, db, p, 1, 1, 0, %66;\n}"
   : "+f"(d[O+0]), "+f"(d[O+1]), "+f"(d[O+2]), "+f"(d[O+3]), "+f"(d[O+4]), "+f"(d[O+5]), "+f"(d[O+6]), "+f"(d[O+7]), "+f"(d[O+8]), "+f"(d[O+9]), "+f"(d[O+10]), "+f"(d[O+11]), "+f"(d[O+12]), "+f"(d[O+13]), "+f"(d[O+14]), "+f"(d[O+15]), "+f"(d[O+16]), "+f"(d[O+17]), "+f"(d[O+18]), "+f"(d[O+19]), "+f"(d[O+20]), "+f"(d[O+21]), "+f"(d[O+22]), "+f"(d[O+23]), "+f"(d[O+24]), "+f"(d[O+25]), "+f"(d[O+26]), "+f"(d[O+27]), "+f"(d[O+28]), "+f"(d[O+29]), "+f"(d[O+30]), "+f"(d[O+31]), "+f"(d[O+32]), "+f"(d[O+33]), "+f"(d[O+34]), "+f"(d[O+35]), "+f"(d[O+36]), "+f"(d[O+37]), "+f"(d[O+38]), "+f"(d[O+39]), "+f"(d[O+40]), "+f"(d[O+41]), "+f"(d[O+42]), "+f"(d[O+43]), "+f"(d[O+44]), "+f"(d[O+45]), "+f"(d[O+46]), "+f"(d[O+47]), "+f"(d[O+48]), "+f"(d[O+49]), "+f"(d[O+50]), "+f"(d[O+51]), "+f"(d[O+52]), "+f"(d[O+53]), "+f"(d[O+54]), "+f"(d[O+55]), "+f"(d[O+56]), "+f"(d[O+57]), "+f"(d[O+58]), "+f"(d[O+59]), "+f"(d[O+60]), "+f"(d[O+61]), "+f"(d[O+62]), "+f"(d[O+63])
   : "r"(da), "r"(db), "n"(TB), "n"(HB), "n"(H128), "r"(sd));
}
template<int O,int TB,int ACC,uint32_t HB = H128,int NN> __device__ __forceinline__ void mma_rs128(float (&d)[NN], uint32_t a0, uint32_t a1, uint32_t a2, uint32_t a3, uint32_t db, int sd = 0){
  if constexpr (ACC == 1) asm volatile("{\n.reg .b64 db;\nmov.b64 db, {%68, %70};\nwgmma.mma_async.sync.aligned.m64n128k16.f32.bf16.bf16 {%0,%1,%2,%3,%4,%5,%6,%7,%8,%9,%10,%11,%12,%13,%14,%15,%16,%17,%18,%19,%20,%21,%22,%23,%24,%25,%26,%27,%28,%29,%30,%31,%32,%33,%34,%35,%36,%37,%38,%39,%40,%41,%42,%43,%44,%45,%46,%47,%48,%49,%50,%51,%52,%53,%54,%55,%56,%57,%58,%59,%60,%61,%62,%63}, {%64,%65,%66,%67}, db, 1, 1, 1, %69;\n}"
   : "+f"(d[O+0]), "+f"(d[O+1]), "+f"(d[O+2]), "+f"(d[O+3]), "+f"(d[O+4]), "+f"(d[O+5]), "+f"(d[O+6]), "+f"(d[O+7]), "+f"(d[O+8]), "+f"(d[O+9]), "+f"(d[O+10]), "+f"(d[O+11]), "+f"(d[O+12]), "+f"(d[O+13]), "+f"(d[O+14]), "+f"(d[O+15]), "+f"(d[O+16]), "+f"(d[O+17]), "+f"(d[O+18]), "+f"(d[O+19]), "+f"(d[O+20]), "+f"(d[O+21]), "+f"(d[O+22]), "+f"(d[O+23]), "+f"(d[O+24]), "+f"(d[O+25]), "+f"(d[O+26]), "+f"(d[O+27]), "+f"(d[O+28]), "+f"(d[O+29]), "+f"(d[O+30]), "+f"(d[O+31]), "+f"(d[O+32]), "+f"(d[O+33]), "+f"(d[O+34]), "+f"(d[O+35]), "+f"(d[O+36]), "+f"(d[O+37]), "+f"(d[O+38]), "+f"(d[O+39]), "+f"(d[O+40]), "+f"(d[O+41]), "+f"(d[O+42]), "+f"(d[O+43]), "+f"(d[O+44]), "+f"(d[O+45]), "+f"(d[O+46]), "+f"(d[O+47]), "+f"(d[O+48]), "+f"(d[O+49]), "+f"(d[O+50]), "+f"(d[O+51]), "+f"(d[O+52]), "+f"(d[O+53]), "+f"(d[O+54]), "+f"(d[O+55]), "+f"(d[O+56]), "+f"(d[O+57]), "+f"(d[O+58]), "+f"(d[O+59]), "+f"(d[O+60]), "+f"(d[O+61]), "+f"(d[O+62]), "+f"(d[O+63])
   : "r"(a0), "r"(a1), "r"(a2), "r"(a3), "r"(db), "n"(TB), "n"(HB));
  else if constexpr (ACC == 0) asm volatile("{\n.reg .b64 db;\nmov.b64 db, {%68, %70};\nwgmma.mma_async.sync.aligned.m64n128k16.f32.bf16.bf16 {%0,%1,%2,%3,%4,%5,%6,%7,%8,%9,%10,%11,%12,%13,%14,%15,%16,%17,%18,%19,%20,%21,%22,%23,%24,%25,%26,%27,%28,%29,%30,%31,%32,%33,%34,%35,%36,%37,%38,%39,%40,%41,%42,%43,%44,%45,%46,%47,%48,%49,%50,%51,%52,%53,%54,%55,%56,%57,%58,%59,%60,%61,%62,%63}, {%64,%65,%66,%67}, db, 0, 1, 1, %69;\n}"
   : "=f"(d[O+0]), "=f"(d[O+1]), "=f"(d[O+2]), "=f"(d[O+3]), "=f"(d[O+4]), "=f"(d[O+5]), "=f"(d[O+6]), "=f"(d[O+7]), "=f"(d[O+8]), "=f"(d[O+9]), "=f"(d[O+10]), "=f"(d[O+11]), "=f"(d[O+12]), "=f"(d[O+13]), "=f"(d[O+14]), "=f"(d[O+15]), "=f"(d[O+16]), "=f"(d[O+17]), "=f"(d[O+18]), "=f"(d[O+19]), "=f"(d[O+20]), "=f"(d[O+21]), "=f"(d[O+22]), "=f"(d[O+23]), "=f"(d[O+24]), "=f"(d[O+25]), "=f"(d[O+26]), "=f"(d[O+27]), "=f"(d[O+28]), "=f"(d[O+29]), "=f"(d[O+30]), "=f"(d[O+31]), "=f"(d[O+32]), "=f"(d[O+33]), "=f"(d[O+34]), "=f"(d[O+35]), "=f"(d[O+36]), "=f"(d[O+37]), "=f"(d[O+38]), "=f"(d[O+39]), "=f"(d[O+40]), "=f"(d[O+41]), "=f"(d[O+42]), "=f"(d[O+43]), "=f"(d[O+44]), "=f"(d[O+45]), "=f"(d[O+46]), "=f"(d[O+47]), "=f"(d[O+48]), "=f"(d[O+49]), "=f"(d[O+50]), "=f"(d[O+51]), "=f"(d[O+52]), "=f"(d[O+53]), "=f"(d[O+54]), "=f"(d[O+55]), "=f"(d[O+56]), "=f"(d[O+57]), "=f"(d[O+58]), "=f"(d[O+59]), "=f"(d[O+60]), "=f"(d[O+61]), "=f"(d[O+62]), "=f"(d[O+63])
   : "r"(a0), "r"(a1), "r"(a2), "r"(a3), "r"(db), "n"(TB), "n"(HB));
  else asm volatile("{\n.reg .pred p;\n.reg .b64 db;\nmov.b64 db, {%68, %70};\nsetp.ne.b32 p, %71, 0;\nwgmma.mma_async.sync.aligned.m64n128k16.f32.bf16.bf16 {%0,%1,%2,%3,%4,%5,%6,%7,%8,%9,%10,%11,%12,%13,%14,%15,%16,%17,%18,%19,%20,%21,%22,%23,%24,%25,%26,%27,%28,%29,%30,%31,%32,%33,%34,%35,%36,%37,%38,%39,%40,%41,%42,%43,%44,%45,%46,%47,%48,%49,%50,%51,%52,%53,%54,%55,%56,%57,%58,%59,%60,%61,%62,%63}, {%64,%65,%66,%67}, db, p, 1, 1, %69;\n}"
   : "+f"(d[O+0]), "+f"(d[O+1]), "+f"(d[O+2]), "+f"(d[O+3]), "+f"(d[O+4]), "+f"(d[O+5]), "+f"(d[O+6]), "+f"(d[O+7]), "+f"(d[O+8]), "+f"(d[O+9]), "+f"(d[O+10]), "+f"(d[O+11]), "+f"(d[O+12]), "+f"(d[O+13]), "+f"(d[O+14]), "+f"(d[O+15]), "+f"(d[O+16]), "+f"(d[O+17]), "+f"(d[O+18]), "+f"(d[O+19]), "+f"(d[O+20]), "+f"(d[O+21]), "+f"(d[O+22]), "+f"(d[O+23]), "+f"(d[O+24]), "+f"(d[O+25]), "+f"(d[O+26]), "+f"(d[O+27]), "+f"(d[O+28]), "+f"(d[O+29]), "+f"(d[O+30]), "+f"(d[O+31]), "+f"(d[O+32]), "+f"(d[O+33]), "+f"(d[O+34]), "+f"(d[O+35]), "+f"(d[O+36]), "+f"(d[O+37]), "+f"(d[O+38]), "+f"(d[O+39]), "+f"(d[O+40]), "+f"(d[O+41]), "+f"(d[O+42]), "+f"(d[O+43]), "+f"(d[O+44]), "+f"(d[O+45]), "+f"(d[O+46]), "+f"(d[O+47]), "+f"(d[O+48]), "+f"(d[O+49]), "+f"(d[O+50]), "+f"(d[O+51]), "+f"(d[O+52]), "+f"(d[O+53]), "+f"(d[O+54]), "+f"(d[O+55]), "+f"(d[O+56]), "+f"(d[O+57]), "+f"(d[O+58]), "+f"(d[O+59]), "+f"(d[O+60]), "+f"(d[O+61]), "+f"(d[O+62]), "+f"(d[O+63])
   : "r"(a0), "r"(a1), "r"(a2), "r"(a3), "r"(db), "n"(TB), "n"(HB), "r"(sd));
}

__host__ __device__ constexpr int brev(int a, int bits) { int r = 0; for (int i = 0; i < bits; i++) r |= ((a >> i) & 1) << (bits - 1 - i); return r; }
__host__ __device__ constexpr int ilog2(int n) { return n <= 1 ? 0 : 1 + ilog2(n / 2); }
template <int SG, int A> __device__ __forceinline__ void bfly(float2& a, float2& b) {
  if constexpr (A == 0) {
    float tr = a.x - b.x, ti = a.y - b.y; a.x += b.x; a.y += b.y; b.x = tr; b.y = ti;
  } else if constexpr (A == 8) {
    float pr = SG > 0 ? -b.y : b.y, pi = SG > 0 ? b.x : -b.x;
    b.x = a.x - pr; b.y = a.y - pi; a.x += pr; a.y += pi;
  } else {
    constexpr float wr = tbl::W32<A>::c, wi = SG * tbl::W32<A>::s;
    float tr = fmaf(wr, b.x, a.x), ti = fmaf(wr, b.y, a.y);
    tr = fmaf(-wi, b.y, tr); ti = fmaf(wi, b.x, ti);
    b.x = fmaf(2.f, a.x, -tr); b.y = fmaf(2.f, a.y, -ti); a.x = tr; a.y = ti;
  }
}
template <int SG, int N, int O, int ST, int A> __device__ __forceinline__ void dft_comb(float2 (&x)[32]) {
  if constexpr (A < N / 2) {
    constexpr int p = O + 2 * ST * brev(A, ilog2(N / 2));
    bfly<SG, A * (32 / N)>(x[p], x[p + ST]);
    dft_comb<SG, N, O, ST, A + 1>(x);
  }
}
template <int SG, int N, int O, int ST> __device__ __forceinline__ void dft(float2 (&x)[32]) {
  if constexpr (N > 1) {
    dft<SG, N / 2, O, 2 * ST>(x);
    dft<SG, N / 2, O + ST, 2 * ST>(x);
    dft_comb<SG, N, O, ST, 0>(x);
  }
}

#define TPACE 150
#define PFMODE 1
#define MAPMODE 0
template <int V> struct IC { static constexpr int value = V; };
struct Maps { CUtensorMap x, ft, fg, e, g64, u64, g32, u32, d192, d32, wr, wi; };

constexpr int NCTA = 132;
constexpr int U = 16384;
constexpr int TB = 36864;
constexpr int OFF_RING = 8 * U, OFF_Z = 9 * U, OFF_WRAW = 12 * U, OFF_T = 13 * U;
constexpr int OFF_BAR = 14 * U;
constexpr int SMEM_BYTES = OFF_BAR + 512;
constexpr int B_FX = 0, B_FA = 8, B_FT = 12, B_Z = 16, B_W = 20, B_HX = 21, B_HT = 22, B_HP = 23;
constexpr int B_EA = 26, B_ET = 30, B_RDY = 34;
constexpr int B_T = 35, NBAR = 36;

__global__ void __cluster_dims__(2, 1, 1) __launch_bounds__(512, 1)
fused_kernel(const __grid_constant__ Maps maps, const __nv_bfloat16* __restrict__ x, const __nv_bfloat16* __restrict__ w_r,
             const __nv_bfloat16* __restrict__ w_i, const __nv_bfloat16* __restrict__ gate_w, const __nv_bfloat16* __restrict__ Wd,
             __nv_bfloat16* __restrict__ out) {
  extern __shared__ __align__(1024) uint8_t smem[];
  const uint32_t sb = smem_u32(smem);
  const uint32_t bars = sb + OFF_BAR;
  const int tid = threadIdx.x, lane = tid & 31;
  const int warp = __shfl_sync(0xffffffffu, tid >> 5, 0);
  const bool helper = blockIdx.x >= 128;
  const int cl = (blockIdx.x >> 1) & 63, rank = blockIdx.x & 1;
  const int q4 = cl & 3, rb = cl >> 2;
  const int j = 2 * q4 + rank;
  const int f_full = 448 * q4 + (rank ? 256 : 0);
  const int f_half = 448 * q4 + (rank ? 224 : 192);
  const int kg = 2 * j + (rb >> 3), tn = rb & 7;

  if (tid == 64) { PROF_EV(0); PROF_CK(40); }
  auto ring_load = [&](int n) {
    const uint32_t fb = bars + 8 * (B_FA + (n & 3)), dst = sb + OFF_RING + (n & 3) * U;
    mbar_expect_tx(fb, U);
    if (n < 8) {
      tma2d(dst, &maps.ft, fb, 64 * n, 64 * j);
      tma2d(dst + 8192, &maps.g32, fb, f_half, 64 * n);
      tma2d(dst + 12288, &maps.u32, fb, f_half, 64 * n);
    } else if (n == 9 || n == 10 || n >= 34) {
      tma4d(dst, &maps.e, fb, 0, 0, 0, 2 * rb + (n >= 34 ? n - 34 : n - 9));
    } else {
      const int q = n == 8 ? 0 : n - 10;
      tma2d(dst, &maps.g64, fb, f_full + 64 * (q >> 3), 64 * (q & 7));
      tma2d(dst + 8192, &maps.u64, fb, f_full + 64 * (q >> 3), 64 * (q & 7));
    }
  };
  auto x_load = [&](int q) {
    mbar_expect_tx(bars + 8 * (B_FX + q), U);
    tma3d(sb + q * U, &maps.x, bars + 8 * (B_FX + q), 64 * q, 0, 2 * rb);
  };
  if (warp >= 12 && lane == 0) {
    if (warp < 14) {
      const int p = warp - 12;
      mbar_init(bars + 8 * (B_FX + p), 1); mbar_init(bars + 8 * (B_FA + p), 1);
      mbar_init(bars + 8 * (B_FX + p + 2), 1); mbar_init(bars + 8 * (B_FA + p + 2), 1);
      asm volatile("fence.proxy.async.shared::cta;" ::: "memory");
      if (!helper) { x_load(p); ring_load(p); }
    } else if (warp == 14) {
#pragma unroll
      for (int i = 4; i < 8; i++) mbar_init(bars + 8 * (B_FX + i), 1);
    } else {
#pragma unroll
      for (int i = B_FT; i < NBAR; i++) mbar_init(bars + 8 * i, i < B_EA ? 1 : i < B_T ? 2 : 4);
#pragma unroll
      for (int i = 0; i < 4; i++) mbar_expect_tx(bars + 8 * (B_Z + i), U);
      asm volatile("fence.mbarrier_init.release.cluster;" ::: "memory");
    }
  }
  __syncthreads();
  asm volatile("barrier.cluster.arrive.relaxed.aligned;" ::: "memory");
  if (tid == 64) PROF_EV(38);

  if (warp >= 12) {
    asm volatile("setmaxnreg.dec.sync.aligned.u32 24;");
    if (lane == 0 && !helper) {
      if (warp == 12) PROF_EV(30);
      if (warp < 14) {
#pragma unroll 1
        for (int n = warp - 10; n < 36; n += 2) {
          if (n >= 4) mbar_wait(bars + 8 * (B_EA + (n & 3)), ((n >> 2) & 1) ^ 1);
          else x_load(n);
          ring_load(n);
          if (n >= 3 && n < 7) x_load(n + 1);
        }
      } else if (warp == 15) {
        const unsigned ep1 = ld_x1(&g_epoch[blockIdx.x * 8]) + 1;
        hint_wait(&g_cntX[32 * j], ep1 * 128u); mbar_arrive(bars + 8 * B_HX);
        hint_wait(&g_cntT[32 * j], ep1 * (j == 0 ? 68u : 64u)); mbar_arrive(bars + 8 * B_HT);
#pragma unroll 1
        for (int i = 0; i < 3; i++) { hint_wait(&g_cntP[32 * (rb * 8 + j) + i], ep1 * 8u); mbar_arrive(bars + 8 * (B_HP + i)); }
      } else {
        PROF_EV(31);
        mbar_wait(bars + 8 * (B_FX + 7), 0);
        PROF_EV(32);
        prefetch2d(rb < 8 ? &maps.g64 : &maps.u64, f_full, 64 * (rb & 7));
        prefetch2d(&maps.g64, f_full + 64 + 64 * (rb >> 3), 64 * (rb & 7));
        prefetch2d(&maps.u64, f_full + 64 + 64 * (rb >> 3), 64 * (rb & 7));
        mbar_expect_tx(bars + 8 * B_W, 24576);
        tma4d(sb + OFF_WRAW, &maps.wr, bars + 8 * B_W, 16 * kg, 0, tn, 0);
        tma4d(sb + OFF_WRAW + 12288, &maps.wi, bars + 8 * B_W, 16 * kg, 0, tn, 0);
        prefetch1d(Wd + (size_t)(224 * j + 14 * rb) * 512, 14336);
#pragma unroll 1
        for (int t = 0; t < 8; t++) {
          const int i = t < 3 ? t + 1 : t < 6 ? t - 2 : 0;
          const int col = 64 * (2 * ((q4 + i) & 3) + ((t < 3 || t == 6) ? 1 - rank : rank));
          const uint32_t fb = bars + 8 * (B_FT + (t & 3)), dst = sb + (t & 3) * TB;
          mbar_wait(bars + 8 * (B_ET + (t & 3)), t >> 2);
          mbar_expect_tx(fb, TB);
          tma2d(dst, &maps.d192, fb, col, f_full);
          tma2d(dst + 24576, &maps.d32, fb, col, f_half);
          tma4d(dst + 28672, &maps.fg, fb, col, 0, 0, 4 * j);
        }
      }
    }
  } else if (warp >= 8) {
    asm volatile("setmaxnreg.dec.sync.aligned.u32 88;");
    const int t = tid - 256, w = warp - 8;
    const float scale = 2.0f / (2048.0f * 512.0f);
    const uint32_t ep = ld_x1(&g_epoch[blockIdx.x * 8]);
    if (!helper) {
      uint4 xv[8], gv[2];
#pragma unroll
      for (int i = 0; i < 4; i++) {
        const int r = 16 * j + 4 * w + i;
        const uint4* p = (const uint4*)(x + (size_t)(2 * rb + (r >> 6) + 32 * (r & 63)) * 512) + lane;
        xv[2 * i] = __ldg(p); xv[2 * i + 1] = __ldg(p + 32);
      }
      gv[0] = __ldg((const uint4*)gate_w + lane); gv[1] = __ldg((const uint4*)gate_w + lane + 32);
      const uint32_t tag = (ep + 1) & 1;
      {
        float z[4];
#pragma unroll
        for (int i = 0; i < 4; i++) {
          float a = 0.f;
#pragma unroll
          for (int hh = 0; hh < 2; hh++) {
            const uint4 u = xv[2 * i + hh], v = gv[hh];
            a = fmaf(bf_lo(u.x), bf_lo(v.x), a); a = fmaf(bf_hi(u.x), bf_hi(v.x), a);
            a = fmaf(bf_lo(u.y), bf_lo(v.y), a); a = fmaf(bf_hi(u.y), bf_hi(v.y), a);
            a = fmaf(bf_lo(u.z), bf_lo(v.z), a); a = fmaf(bf_hi(u.z), bf_hi(v.z), a);
            a = fmaf(bf_lo(u.w), bf_lo(v.w), a); a = fmaf(bf_hi(u.w), bf_hi(v.w), a);
          }
#pragma unroll
          for (int o = 16; o; o >>= 1) a += __shfl_xor_sync(0xffffffffu, a, o);
          z[i] = a;
        }
        if (lane < 4) {
          const float zz = lane == 0 ? z[0] : lane == 1 ? z[1] : lane == 2 ? z[2] : z[3];
          asm volatile("st.relaxed.gpu.global.f32 [%0], %1;" ::"l"(g_gate + rb * 128 + 16 * j + 4 * w + lane), "f"(tagf(1.0f / (1.0f + __expf(-zz)), tag)) : "memory");
        }
        if (t == 0) PROF_EV(18);
      }
      if (w == 0) {
        const int c = lane >> 4, jj = 16 * blockIdx.x + (lane & 15), jm = (2048 - jj) & 2047;
        const unsigned short* pr = (const unsigned short*)w_r + 256 * c;
        const unsigned short* pi = (const unsigned short*)w_i + 256 * c;
        const float wr = 0.5f * (bf_lo(__ldg(pr + jj * 257)) + bf_lo(__ldg(pr + jm * 257)));
        const float wi = 0.5f * (bf_lo(__ldg(pi + jj * 257)) - bf_lo(__ldg(pi + jm * 257)));
        st_x2(g_Wh + c * 2048 + jj, tagf(c ? -wi : wr, tag), c ? wr : wi);
        __syncwarp();
        if (lane == 0) hint_add(&g_cntW[0]);
      }
      const int k = 16 * kg + (t & 15), j1 = 8 * tn + (t >> 4);
      {
        const unsigned short* p = (const unsigned short*)(smem + OFF_WRAW) + (t >> 4) * 25 + (t & 15);
        uint32_t wv[32];
        mbar_wait(bars + 8 * B_W, 0);
#pragma unroll
        for (int a = 0; a < 32; a++) wv[a] = (uint32_t)p[a * 192] | ((uint32_t)p[6144 + a * 192] << 16);
        asm volatile("bar.sync 1, 128;" ::: "memory");
#pragma unroll
        for (int a = 0; a < 8; a++) *(uint4*)(smem + OFF_WRAW + (a * 128 + t) * 16) = make_uint4(wv[4 * a], wv[4 * a + 1], wv[4 * a + 2], wv[4 * a + 3]);
      }
      if (t == 0) PROF_EV(11);
      mbar_wait(bars + 8 * B_HX, 0);
      float2 v[32];
      if (t == 0) PROF_EV(22);
      load32_tagged(v, (const float2*)g_X1p + (size_t)(kg * 8 + tn) * 2048 + ((t >> 3) & 1) * 32 + w * 8 + (t & 7), 64, tag);
#pragma unroll
      for (int a = 0; a < 32; a++) {
        const uint32_t u = __float_as_uint((t & 16) ? v[a].y : v[a].x);
        v[a] = make_float2(bf_lo(u), bf_hi(u));
      }
      if (t == 0) PROF_EV(12);
      dft<-1, 32, 0, 1>(v);
      float2 y[32];
#pragma unroll
      for (int a4 = 0; a4 < 8; a4++) {
        const uint4 ww = *(const uint4*)(smem + OFF_WRAW + (a4 * 128 + t) * 16);
        const uint32_t wq[4] = {ww.x, ww.y, ww.z, ww.w};
#pragma unroll
        for (int e = 0; e < 4; e++) {
          const float2 z = v[brev(4 * a4 + e, 5)];
          const float wr = bf_lo(wq[e]), wi = bf_hi(wq[e]);
          y[4 * a4 + e] = make_float2(fmaf(z.x, wr, -z.y * wi), fmaf(z.x, wi, z.y * wr));
        }
      }
      dft<1, 32, 0, 1>(y);
      if (t == 0) PROF_EV(16);
      {
        uint2* dst = g_T + (size_t)j * 32768 + (kg & 1) * 1024 + j1 * 16 + (t & 15);
#pragma unroll
        for (int a = 0; a < 16; a++) {
          const float2 u0 = y[brev(2 * a, 5)], u1 = y[brev(2 * a + 1, 5)];
          if (k != 0) st_u2(dst + a * 2048, (pack_bf16(u0.x * scale, u0.y * scale) & ~1u) | tag, pack_bf16(u1.x * scale, u1.y * scale));
          if (TPACE && (a & 3) == 3 && a < 15) __nanosleep(TPACE);
        }
        __syncwarp();
        if (lane == 0) hint_add(&g_cntT[32 * j]);
      }
      if (t == 0) PROF_EV(17);
      {
        const uint4* src = (const uint4*)(g_T + (size_t)(j * 16 + rb) * 2048) + t;
        uint4 u[8];
        mbar_wait(bars + 8 * B_HT, 0);
        if (t == 0) PROF_EV(23);
        const uint32_t t0 = (uint32_t)clock();
        for (;;) {
          uint32_t bad = 0;
#pragma unroll
          for (int a = 0; a < 8; a++) u[a] = ld_x4(src + a * 128);
#pragma unroll
          for (int a = 0; a < 8; a++) bad |= (u[a].x ^ tag) | (u[a].z ^ tag);
          if (!__any_sync(0xffffffffu, bad & 1)) break;
          spin_guard(t0);
        }
        const int r = t >> 3, c = t & 7;
#pragma unroll
        for (int a = 0; a < 8; a++) {
          const uint32_t dst = sb + OFF_T + (16 * (a & 3) + r) * 128 + ((((a >> 2) * 4 + (c >> 1)) ^ (r & 7)) << 4) + (c & 1) * 8;
          asm volatile("st.shared.v2.u32 [%0], {%1,%2};" ::"r"(dst), "r"(u[a].x & ~1u), "r"(u[a].z & ~1u) : "memory");
          asm volatile("st.shared.v2.u32 [%0], {%1,%2};" ::"r"(dst + 8192), "r"(u[a].y), "r"(u[a].w) : "memory");
        }
        asm volatile("fence.proxy.async.shared::cta;" ::: "memory");
        __syncwarp();
        if (lane == 0) mbar_arrive(bars + 8 * B_T);
        if (t == 0) PROF_EV(13);
      }
    } else if (w == 0) {
      const uint32_t tag = (ep + 1) & 1;
      const int c = lane >> 4, j1 = 16 * (blockIdx.x - 128) + (lane & 15);
      float2* wf = (float2*)smem;
      float2 v[32];
      hint_wait(&g_cntW[0], (ep + 1) * 128u);
      load32_tagged(v, g_Wh + c * 2048 + j1, 64, tag);
#pragma unroll
      for (int a = 0; a < 32; a++) wf[a * 32 + lane] = v[a];
      if (t == 0) PROF_EV(11);
      hint_wait(&g_cntX[0], (ep + 1) * 128u);
      load32_tagged(v, g_X1s + c * 2048 + j1, 64, tag);
      if (t == 0) PROF_EV(12);
      dft<-1, 32, 0, 1>(v);
      float2 y[32];
#pragma unroll
      for (int a = 0; a < 32; a++) {
        const float2 z = v[brev(a, 5)], wv = wf[a * 32 + lane];
        y[a] = make_float2(fmaf(z.x, wv.x, -z.y * wv.y), fmaf(z.x, wv.y, z.y * wv.x));
      }
      dft<1, 32, 0, 1>(y);
      if (t == 0) PROF_EV(16);
#pragma unroll
      for (int a = 0; a < 8; a++) {
        uint32_t pk[2];
#pragma unroll
        for (int e = 0; e < 2; e++) {
          const float2 u0 = y[brev(4 * a + e, 5)], u1 = y[brev(4 * a + 2 + e, 5)];
          const float2 keep = c ? u1 : u0, give = c ? u0 : u1;
          const float ox = __shfl_xor_sync(0xffffffffu, give.x, 16), oy = __shfl_xor_sync(0xffffffffu, give.y, 16);
          pk[e] = pack_bf16((keep.x + ox) * (0.5f * scale), (keep.y + oy) * (0.5f * scale));
        }
        st_u2(g_T + (2 * a + c) * 2048 + j1 * 16, (pk[0] & ~1u) | tag, pk[1]);
      }
      __syncwarp();
      if (t == 0) { hint_add(&g_cntT[0]); g_epoch[blockIdx.x * 8] = ep + 1; PROF_EV(13); }
    }
  } else {
    asm volatile("setmaxnreg.inc.sync.aligned.u32 200;");
    if (!helper) {
      const int wg = warp >> 2, w = warp & 3, g = lane >> 2, q = lane & 3;
      const bool elect = (tid & 127) == 0;
      const uint32_t ep = ld_x1(&g_epoch[blockIdx.x * 8]);
      float c1[64], cA[64], c2[64], ci[64], ct[64];
      const int zero = blockIdx.x >> 16;
      uint32_t h[56], yf[16];
      const uint32_t d0 = (sb & 0x3FFFF) >> 4;
      const uint32_t dK = d0 | (1u << 16), dN = d0 | (512u << 16), dM = d0 | (256u << 16);
      const uint32_t dX = dK + wg * 512;
      constexpr uint32_t RING = OFF_RING >> 4;
      auto waitA = [&](int n) { mbar_wait(bars + 8 * (B_FA + (n & 3)), (n >> 2) & 1); };
      auto freeA = [&](int n) { if (elect) mbar_arrive(bars + 8 * (B_EA + (n & 3))); };

      auto c1_step = [&](auto first, int kb) {
        mbar_wait(bars + 8 * (B_FX + kb), 0); waitA(kb);
        wg_fence();
        const uint32_t dx = dX + kb * 1024, df = dK + RING + (kb & 3) * 1024, dm = dM + RING + 512 + (kb & 3) * 1024;
        mma_ss64<0, 0, decltype(first)::value>(c1, df, dx);
        mma_ss64<32, 1, decltype(first)::value, H64>(c1, dx, dm);
#pragma unroll
        for (int k = 1; k < 4; k++) {
          mma_ss64<0, 0, 1>(c1, df + k * 2, dx + k * 2);
          mma_ss64<32, 1, 1, H64>(c1, dx + k * 2, dm + k * 64);
        }
        wg_commit();
      };
      c1_step(IC<0>(), 0);
      if (tid == 0) PROF_EV(1);
#pragma unroll 1
      for (int kb = 1; kb < 8; kb++) { c1_step(IC<1>(), kb); wg_wait<1>(); freeA(kb - 1); }
      auto ffn_step = [&](auto first, float (&acc)[64], int n, int kb) {
        waitA(n);
        wg_fence();
        const uint32_t dx = dX + kb * 1024, db = dN + RING + (n & 3) * 1024;
        mma_ss128<0, 1, decltype(first)::value>(acc, dx, db, zero);
#pragma unroll
        for (int k = 1; k < 4; k++) mma_ss128<0, 1, 1>(acc, dx + k * 2, db + k * 128);
        wg_commit();
        wg_wait<1>();
      };
      const uint32_t tag = (ep + 1) & 1;
      const float* gp = g_gate + rb * 128 + wg * 64 + w * 16 + g;
      uint32_t gb0 = ld_x1(gp), gb1 = ld_x1(gp + 8);
      ffn_step(IC<0>(), c2, 8, 0);
      freeA(7);
      fence_regs<0, 64>(c1);
      if (tid == 0) PROF_EV(2);
#pragma unroll
      for (int i = 0; i < 16; i++) yf[i] = pack_pin(c1[2 * i], c1[2 * i + 1]);
      {
        const uint32_t t0 = (uint32_t)clock();
        while (((gb0 ^ tag) | (gb1 ^ tag)) & 1) { gb0 = ld_x1(gp); gb1 = ld_x1(gp + 8); spin_guard(t0); }
        __syncwarp();
      }
      if (tid == 0) PROF_EV(10);
      const float g0 = __uint_as_float(gb0 & ~1u), g1 = __uint_as_float(gb1 & ~1u);
      const float o0 = 1.0f - g0, o1 = 1.0f - g1;
#pragma unroll
      for (int i = 0; i < 8; i++) {
        const float o = (i & 1) ? o1 : o0;
        h[48 + i] = pack_pin(fmaxf(c1[32 + 2 * i], 0.f) * c1[48 + 2 * i] * o, fmaxf(c1[33 + 2 * i], 0.f) * c1[49 + 2 * i] * o);
      }
      {
        waitA(9); waitA(10);
        const uint32_t de = dN + RING + (1 + wg) * 1024;
        wg_fence();
        mma_rs128<0, 1, 0>(cA, yf[0], yf[1], yf[2], yf[3], de);
#pragma unroll
        for (int k = 1; k < 4; k++) mma_rs128<0, 1, 1>(cA, yf[4 * k], yf[4 * k + 1], yf[4 * k + 2], yf[4 * k + 3], de + k * 128);
        wg_commit();
        wg_wait<1>();
        freeA(8);
        ffn_step(IC<1>(), c2, 11, 1);
        freeA(9); freeA(10);
        fence_regs<0, 64>(cA);
        if (tid == 0) PROF_EV(19);
        const int s0 = 2 * rb + wg;
        uint2* dst = g_X1p + ((size_t)((2 * j + (w >> 1)) * 8) * 32 + s0) * 64 + (w & 1) * 32 + q * 8 + g;
        auto x1_store = [&](int n0, int n1) {
#pragma unroll
          for (int n = n0; n < n1; n++)
            st_u2(dst + n * 2048, (pack_bf16(cA[4 * n] - cA[34 + 4 * n], cA[32 + 4 * n] + cA[4 * n + 2]) & ~1u) | tag,
                  pack_bf16(cA[4 * n + 1] - cA[35 + 4 * n], cA[33 + 4 * n] + cA[4 * n + 3]));
        };
        if (j == 0 && w == 0 && g == 0) {
#pragma unroll
          for (int n = 0; n < 8; n++) {
#pragma unroll
            for (int e = 0; e < 2; e++) {
              st_x2(g_X1s + s0 * 64 + 8 * n + 2 * q + e, tagf(cA[4 * n + e], tag), cA[32 + 4 * n + e]);
              st_x2(g_X1s + (32 + s0) * 64 + 8 * n + 2 * q + e, tagf(cA[4 * n + 2 + e], tag), cA[34 + 4 * n + e]);
            }
          }
        }
        __syncwarp();
        x1_store(0, 3);
        ffn_step(IC<1>(), c2, 12, 2); freeA(11);
        x1_store(3, 6);
        ffn_step(IC<1>(), c2, 13, 3); freeA(12);
        x1_store(6, 8);
        __syncwarp();
        if (lane == 0) hint_add(&g_cntX[32 * j]);
        if (tid == 0) PROF_EV(3);
      }
      auto glu = [&](float (&acc)[64], int ho) {
#pragma unroll
        for (int i = 0; i < 16; i++) {
          const float o = (i & 1) ? o1 : o0;
          h[ho + i] = pack_pin(fmaxf(acc[2 * i], 0.f) * acc[32 + 2 * i] * o, fmaxf(acc[2 * i + 1], 0.f) * acc[33 + 2 * i] * o);
        }
      };
#pragma unroll 1
      for (int kb = 4; kb < 8; kb++) { ffn_step(IC<1>(), c2, 10 + kb, kb); freeA(9 + kb); }
      ffn_step(IC<2>(), cA, 18, 0); freeA(17);
      fence_regs<0, 64>(c2);
      if (tid == 0) PROF_EV(4);
      glu(c2, 0);
#pragma unroll 1
      for (int kb = 1; kb < 8; kb++) { ffn_step(IC<1>(), cA, 18 + kb, kb); freeA(17 + kb); }
      ffn_step(IC<2>(), c2, 26, 0); freeA(25);
      fence_regs<0, 64>(cA);
      if (tid == 0) PROF_EV(5);
      glu(cA, 16);
#pragma unroll 1
      for (int kb = 1; kb < 8; kb++) {
        ffn_step(IC<1>(), c2, 26 + kb, kb); freeA(25 + kb);
        if (elect && kb >= 3 && (kb & 1)) mbar_arrive(bars + 8 * (B_ET + ((kb - 3) >> 1)));
      }
      wg_wait<0>();
      if (elect) mbar_arrive(bars + 8 * (B_ET + 3));
      fence_regs<0, 64>(c2);
      glu(c2, 32);
      waitA(34 + wg);
      if (tid == 0) PROF_EV(6);
      mbar_wait(bars + 8 * B_T, 0);
      if (tid == 0) PROF_EV(7);
      wg_fence();
      {
        const uint32_t dt = dN + (OFF_T >> 4) + wg * 512, de = dK + RING + (2 + wg) * 1024;
        mma_ss64<0, 1, 0>(ci, de, dt);
        mma_ss64<32, 1, 0>(ci, de + 512, dt);
#pragma unroll
        for (int k = 1; k < 4; k++) {
          mma_ss64<0, 1, 1>(ci, de + k * 2, dt + k * 128);
          mma_ss64<32, 1, 1>(ci, de + (512 + k * 2), dt + k * 128);
        }
      }
      wg_commit();

      auto head = [&](auto off, int t) {
        constexpr int O = decltype(off)::value;
        mbar_wait(bars + 8 * (B_FT + (t & 3)), t >> 2);
        const uint32_t db = dN + (t & 3) * (TB >> 4);
        wg_fence();
        mma_rs64<O, 1, 0>(ct, h[0], h[1], h[2], h[3], db);
#pragma unroll
        for (int k = 1; k < 6; k++) mma_rs64<O, 1, 1>(ct, h[4 * k], h[4 * k + 1], h[4 * k + 2], h[4 * k + 3], db + k * 128);
        wg_commit();
        wg_wait<1>();
      };
      auto rest = [&](auto off, int t) {
        constexpr int O = decltype(off)::value;
        const uint32_t db = dN + (t & 3) * (TB >> 4);
        wg_fence();
#pragma unroll
        for (int k = 6; k < 14; k++) mma_rs64<O, 1, 1>(ct, h[4 * k], h[4 * k + 1], h[4 * k + 2], h[4 * k + 3], db + k * 128);
#pragma unroll
        for (int k = 0; k < 4; k++) mma_rs64<O, 1, 1>(ct, yf[4 * k], yf[4 * k + 1], yf[4 * k + 2], yf[4 * k + 3], db + (14 + k) * 128);
        wg_commit();
      };
      auto freeT = [&](int t) { if (elect) mbar_arrive(bars + 8 * (B_ET + t)); };
      const uint32_t peerZ = mapa(sb + OFF_Z + tid * 16, rank ^ 1), peerB = mapa(bars + 8 * B_Z, rank ^ 1);
      auto send_peer = [&](auto off, int z) {
        constexpr int O = decltype(off)::value;
        fence_regs<O, 32>(ct);
#pragma unroll
        for (int i = 0; i < 4; i++)
          asm volatile("st.async.weak.shared::cluster.mbarrier::complete_tx::bytes.v4.b32 [%0], {%1,%2,%3,%4}, [%5];" ::"r"(peerZ + z * U + i * 4096),
                       "r"(pack_bf16(ct[O + 8 * i], ct[O + 8 * i + 1])), "r"(pack_bf16(ct[O + 8 * i + 2], ct[O + 8 * i + 3])),
                       "r"(pack_bf16(ct[O + 8 * i + 4], ct[O + 8 * i + 5])), "r"(pack_bf16(ct[O + 8 * i + 6], ct[O + 8 * i + 7])), "r"(peerB + 8 * z) : "memory");
      };
      auto send_grid = [&](auto off, int z) {
        constexpr int O = decltype(off)::value;
        fence_regs<O, 32>(ct);
        mbar_wait(bars + 8 * (B_Z + z), 0);
        uint4* dst = g_part + (size_t)((rb * 8 + 2 * ((q4 + z + 1) & 3) + rank) * 3 + z) * 1024 + tid;
#pragma unroll
        for (int i = 0; i < 4; i++) {
          const uint4 p = *(const uint4*)(smem + OFF_Z + z * U + i * 4096 + tid * 16);
          st_x4(dst + i * 256, (pack_bf16(ct[O + 8 * i] + bf_lo(p.x), ct[O + 8 * i + 1] + bf_hi(p.x)) & ~1u) | tag,
                pack_bf16(ct[O + 8 * i + 2] + bf_lo(p.y), ct[O + 8 * i + 3] + bf_hi(p.y)),
                pack_bf16(ct[O + 8 * i + 4] + bf_lo(p.z), ct[O + 8 * i + 5] + bf_hi(p.z)),
                pack_bf16(ct[O + 8 * i + 6] + bf_lo(p.w), ct[O + 8 * i + 7] + bf_hi(p.w)));
        }
        __syncwarp();
        if (lane == 0) hint_add(&g_cntP[32 * (rb * 8 + 2 * ((q4 + z + 1) & 3) + rank) + z]);
      };
      asm volatile("barrier.cluster.wait.aligned;" ::: "memory");
      head(IC<0>(), 0);
      if (elect) asm volatile("mbarrier.arrive.shared::cluster.b64 _, [%0];" ::"r"(mapa(bars + 8 * B_RDY, rank ^ 1)) : "memory");
      fence_regs<0, 64>(ci);
#pragma unroll
      for (int i = 0; i < 16; i++) {
        const float gg = (i & 1) ? g1 : g0;
        yf[i] = pack_pin((ci[2 * i] + ci[33 + 2 * i]) * gg, (ci[2 * i + 1] - ci[32 + 2 * i]) * gg);
      }
      rest(IC<0>(), 0);
      if (tid == 0) PROF_EV(8);
      head(IC<32>(), 1); freeT(0); mbar_wait(bars + 8 * B_RDY, 0); send_peer(IC<0>(), 0); rest(IC<32>(), 1);
      head(IC<0>(), 2); freeT(1); send_peer(IC<32>(), 1); rest(IC<0>(), 2);
      head(IC<32>(), 3); freeT(2); send_peer(IC<0>(), 2); rest(IC<32>(), 3);
      head(IC<0>(), 4); freeT(3); send_grid(IC<32>(), 0); rest(IC<0>(), 4);
      head(IC<32>(), 5); send_grid(IC<0>(), 1); rest(IC<32>(), 5);
      head(IC<0>(), 6); send_grid(IC<32>(), 2); rest(IC<0>(), 6);
      head(IC<32>(), 7); send_peer(IC<0>(), 3);
      {
        const uint4* src = g_part + (size_t)(rb * 8 + j) * 3 * 1024 + tid;
        uint4 pv[12];
        mbar_wait(bars + 8 * (B_HP + 1), 0);
#pragma unroll
        for (int i = 0; i < 8; i++) pv[i] = ld_x4(src + i * 256);
        rest(IC<32>(), 7);
        if (tid == 0) PROF_EV(9);
        mbar_wait(bars + 8 * (B_HP + 2), 0);
        if (tid == 0) PROF_EV(24);
#pragma unroll
        for (int i = 8; i < 12; i++) pv[i] = ld_x4(src + i * 256);
        const uint32_t t0 = (uint32_t)clock();
        for (;;) {
          uint32_t bad = 0;
#pragma unroll
          for (int i = 0; i < 12; i++) bad |= pv[i].x ^ tag;
          if (!__any_sync(0xffffffffu, bad & 1)) break;
#pragma unroll
          for (int i = 0; i < 12; i++) pv[i] = ld_x4(src + i * 256);
          spin_guard(t0);
        }
        if (tid == 0) PROF_EV(14);
        float sum[32];
#pragma unroll
        for (int i = 0; i < 4; i++) {
          const uint32_t a[4] = {pv[i].x & ~1u, pv[i].y, pv[i].z, pv[i].w}, b[4] = {pv[4 + i].x & ~1u, pv[4 + i].y, pv[4 + i].z, pv[4 + i].w},
                         c[4] = {pv[8 + i].x & ~1u, pv[8 + i].y, pv[8 + i].z, pv[8 + i].w};
#pragma unroll
          for (int e = 0; e < 4; e++) {
            sum[8 * i + 2 * e] = bf_lo(a[e]) + bf_lo(b[e]) + bf_lo(c[e]);
            sum[8 * i + 2 * e + 1] = bf_hi(a[e]) + bf_hi(b[e]) + bf_hi(c[e]);
          }
        }
        mbar_wait(bars + 8 * (B_Z + 3), 0);
#pragma unroll
        for (int i = 0; i < 4; i++) {
          const uint4 p = *(const uint4*)(smem + OFF_Z + 3 * U + i * 4096 + tid * 16);
          const uint32_t a[4] = {p.x, p.y, p.z, p.w};
#pragma unroll
          for (int e = 0; e < 4; e++) { sum[8 * i + 2 * e] += bf_lo(a[e]); sum[8 * i + 2 * e + 1] += bf_hi(a[e]); }
        }
        wg_wait<0>();
        fence_regs<32, 32>(ct);
#pragma unroll
        for (int i = 0; i < 32; i++) sum[i] += ct[32 + i];
        const uint32_t stg = sb + OFF_T + warp * 2048;
        const int mr = (lane & 7) + ((lane >> 3) & 1) * 8, mc = lane >> 4;
#pragma unroll
        for (int i = 0; i < 4; i++) {
          const uint32_t a = stg + mr * 128 + (((2 * i + mc) ^ (mr & 7)) << 4);
          asm volatile("stmatrix.sync.aligned.m8n8.x4.shared.b16 [%0], {%1,%2,%3,%4};" ::"r"(a), "r"(pack_bf16(sum[8 * i], sum[8 * i + 1])),
                       "r"(pack_bf16(sum[8 * i + 2], sum[8 * i + 3])), "r"(pack_bf16(sum[8 * i + 4], sum[8 * i + 5])),
                       "r"(pack_bf16(sum[8 * i + 6], sum[8 * i + 7])) : "memory");
        }
        __syncwarp();
#pragma unroll
        for (int i = 0; i < 4; i++) {
          const int r = 4 * i + (lane >> 3), c = lane & 7;
          const uint4 v = *(const uint4*)(smem + OFF_T + warp * 2048 + r * 128 + ((c ^ (r & 7)) << 4));
          *(uint4*)(out + (size_t)(2 * rb + wg + 32 * (16 * w + r)) * 512 + 64 * j + 8 * c) = v;
        }
      }
      if (tid == 0) { g_epoch[blockIdx.x * 8] = ep + 1; PROF_EV(15); PROF_CK(41); }
    }
  }
}

typedef CUresult (*EncodeFn)(CUtensorMap*, CUtensorMapDataType, cuuint32_t, void*, const cuuint64_t*, const cuuint64_t*, const cuuint32_t*,
                             const cuuint32_t*, CUtensorMapInterleave, CUtensorMapSwizzle, CUtensorMapL2promotion, CUtensorMapFloatOOBfill);

static void encode(EncodeFn f, CUtensorMap* m, const void* base, int rank, const cuuint64_t* dims, const cuuint64_t* strides, const cuuint32_t* box,
                   CUtensorMapSwizzle sw) {
  cuuint32_t es[5] = {1, 1, 1, 1, 1};
  f(m, CU_TENSOR_MAP_DATA_TYPE_BFLOAT16, rank, (void*)base, dims, strides, box, es, CU_TENSOR_MAP_INTERLEAVE_NONE, sw,
    CU_TENSOR_MAP_L2_PROMOTION_L2_128B, CU_TENSOR_MAP_FLOAT_OOB_FILL_NONE);
}

extern "C" void kernel_launch(void* const* d_in, const int* in_sizes, int n_in, void* d_out, int out_size) {
  (void)in_sizes; (void)n_in; (void)out_size;
  const __nv_bfloat16* x = (const __nv_bfloat16*)d_in[0];
  const __nv_bfloat16* w_r = (const __nv_bfloat16*)d_in[1];
  const __nv_bfloat16* w_i = (const __nv_bfloat16*)d_in[2];
  const __nv_bfloat16* Wg = (const __nv_bfloat16*)d_in[4];
  const __nv_bfloat16* Wu = (const __nv_bfloat16*)d_in[5];
  const __nv_bfloat16* Wd = (const __nv_bfloat16*)d_in[6];
  const __nv_bfloat16* gw = (const __nv_bfloat16*)d_in[7];

  void* fp = nullptr; cudaDriverEntryPointQueryResult qr;
  cudaGetDriverEntryPoint("cuTensorMapEncodeTiled", &fp, cudaEnableDefault, &qr);
  EncodeFn enc = (EncodeFn)fp;
  void *pFT, *pET;
  cudaGetSymbolAddress(&pFT, g_FT); cudaGetSymbolAddress(&pET, g_ET);

  Maps mp;
  const CUtensorMapSwizzle S128 = CU_TENSOR_MAP_SWIZZLE_128B, S64 = CU_TENSOR_MAP_SWIZZLE_64B;
  { cuuint64_t d[3] = {512, 64, 32}, s[2] = {32768, 1024}; cuuint32_t b[3] = {64, 64, 2}; encode(enc, &mp.x, x, 3, d, s, b, S128); }
  { cuuint64_t d[2] = {512, 512}, s[1] = {1024}; cuuint32_t b[2] = {64, 64}; encode(enc, &mp.ft, pFT, 2, d, s, b, S128); }
  { cuuint64_t d[4] = {512, 2, 8, 32}, s[3] = {8192, 1024, 16384}; cuuint32_t b[4] = {64, 2, 8, 4}; encode(enc, &mp.fg, pFT, 4, d, s, b, S128); }
  { cuuint64_t d[4] = {64, 64, 2, 32}, s[3] = {8192, 128, 256}; cuuint32_t b[4] = {64, 64, 2, 1}; encode(enc, &mp.e, pET, 4, d, s, b, S128); }
  { cuuint64_t d[2] = {1792, 512}, s[1] = {3584}; cuuint32_t b[2] = {64, 64}, b2[2] = {32, 64};
    encode(enc, &mp.g64, Wg, 2, d, s, b, S128); encode(enc, &mp.u64, Wu, 2, d, s, b, S128);
    encode(enc, &mp.g32, Wg, 2, d, s, b2, S64); encode(enc, &mp.u32, Wu, 2, d, s, b2, S64); }
  { cuuint64_t d[2] = {512, 1792}, s[1] = {1024}; cuuint32_t b[2] = {64, 192}, b2[2] = {64, 32};
    encode(enc, &mp.d192, Wd, 2, d, s, b, S128); encode(enc, &mp.d32, Wd, 2, d, s, b2, S128); }

  { cuuint64_t d[4] = {264, 8, 8, 32}, s[3] = {512, 4112, 32896}; cuuint32_t b[4] = {24, 8, 1, 32};
    encode(enc, &mp.wr, w_r, 4, d, s, b, CU_TENSOR_MAP_SWIZZLE_NONE); encode(enc, &mp.wi, w_i, 4, d, s, b, CU_TENSOR_MAP_SWIZZLE_NONE); }

  cudaFuncSetAttribute(fused_kernel, cudaFuncAttributeMaxDynamicSharedMemorySize, SMEM_BYTES);
  fused_kernel<<<NCTA, 512, SMEM_BYTES>>>(mp, x, w_r, w_i, gw, Wd, (__nv_bfloat16*)d_out);
}
```

```cpp
#include <cuda_runtime.h>
#include <cuda_bf16.h>
#include <cuda.h>
#include <stdint.h>

namespace tbl {
constexpr double PI = 3.14159265358979323846264338327950288;
constexpr double sin_s(double x) { double t = x, s = x; for (int n = 1; n < 12; n++) { t *= -x * x / ((2 * n) * (2 * n + 1)); s += t; } return s; }
constexpr double cos_s(double x) { double t = 1, s = 1; for (int n = 1; n < 12; n++) { t *= -x * x / ((2 * n - 1) * (2 * n)); s += t; } return s; }
constexpr double cos2048(int m) {
  m &= 2047; if (m > 1024) m = 2048 - m;
  bool neg = false; if (m > 512) { m = 1024 - m; neg = true; }
  double v = (m <= 256) ? cos_s(2 * PI * m / 2048) : sin_s(2 * PI * (512 - m) / 2048);
  return neg ? -v : v;
}
constexpr uint16_t to_bf16(double v) {
  if (v == 0) return 0;
  uint16_t s = 0; if (v < 0) { s = 0x8000; v = -v; }
  int e = 0; while (v >= 2) { v /= 2; e++; } while (v < 1) { v *= 2; e--; }
  double m = (v - 1) * 128; int mi = (int)m; double fr = m - mi;
  if (fr > 0.5 || (fr == 0.5 && (mi & 1))) mi++;
  if (mi == 128) { mi = 0; e++; }
  return (uint16_t)(s | ((e + 127) << 7) | mi);
}
struct CosT { uint16_t v[2048]; constexpr CosT() : v() { for (int i = 0; i < 2048; i++) v[i] = to_bf16(cos2048(i)); } };
struct alignas(1024) FT {
  uint16_t v[512 * 512];
  constexpr FT() : v() {
    CosT c;
    for (int r = 0; r < 512; r++) {
      int k = (r >> 4) * 8 + (r & 7), e = (r >> 3) & 1;
      int mul = 4 * k, add = e ? 512 : 0;
      if (k == 0 && e == 1) { mul = 1024; add = 0; }
      for (int d = 0; d < 512; d++) v[r * 512 + d] = c.v[(d * mul + add) & 2047];
    }
  }
};
struct alignas(1024) ET {
  uint16_t v[2048 * 128];
  constexpr ET() : v() {
    CosT c;
    for (int s = 0; s < 2048; s++)
      for (int j = 0; j < 64; j++) { v[s * 128 + j] = c.v[(s * j) & 2047]; v[s * 128 + 64 + j] = c.v[(s * j + 512) & 2047]; }
  }
};
template <int A> struct W32 {
  static constexpr float c = (float)cos2048(A * 64);
  static constexpr float s = (float)cos2048(A * 64 - 512);
};
}

__device__ constexpr tbl::FT g_FT = tbl::FT();
__device__ constexpr tbl::ET g_ET = tbl::ET();

__device__ __align__(1024) uint2 g_X1p[128 * 32 * 64];
__device__ __align__(1024) float2 g_X1s[2 * 32 * 64];
__device__ __align__(1024) uint2 g_T[8 * 16 * 2 * 64 * 16];
__device__ __align__(1024) uint4 g_part[128 * 3 * 1024];
__device__ __align__(16) float g_gate[16 * 128];
__device__ __align__(16) float2 g_Wh[2 * 2048];
__device__ unsigned g_epoch[132 * 8];
__device__ unsigned g_cntX[8 * 32], g_cntT[8 * 32], g_cntP[128 * 32], g_cntW[32];
#define PROF_EV(i) do {} while (0)
#define PROF_CK(i) do {} while (0)

__device__ __forceinline__ uint32_t smem_u32(const void* p) { return (uint32_t)__cvta_generic_to_shared(p); }
__device__ __forceinline__ void mbar_init(uint32_t bar, uint32_t cnt) { asm volatile("mbarrier.init.shared::cta.b64 [%0], %1;" ::"r"(bar), "r"(cnt)); }
__device__ __forceinline__ void mbar_expect_tx(uint32_t bar, uint32_t bytes) { asm volatile("mbarrier.arrive.expect_tx.shared::cta.b64 _, [%0], %1;" ::"r"(bar), "r"(bytes) : "memory"); }
__device__ __forceinline__ void mbar_arrive(uint32_t bar) { asm volatile("mbarrier.arrive.shared::cta.b64 _, [%0];" ::"r"(bar) : "memory"); }
__device__ __forceinline__ bool mbar_try(uint32_t bar, uint32_t parity) {
  uint32_t ok;
  asm volatile("{\n.reg .pred p;\nmbarrier.try_wait.parity.shared::cta.b64 p, [%1], %2;\nselp.u32 %0, 1, 0, p;\n}" : "=r"(ok) : "r"(bar), "r"(parity) : "memory");
  return ok;
}
__device__ __forceinline__ void mbar_wait(uint32_t bar, uint32_t parity) {
  if (mbar_try(bar, parity)) return;
  const uint32_t t0 = (uint32_t)clock();
  while (!mbar_try(bar, parity)) { if ((uint32_t)clock() - t0 > (1u << 30)) __trap(); }
}
__device__ __forceinline__ void spin_guard(uint32_t t0) { if ((uint32_t)clock() - t0 > (1u << 30)) __trap(); }
__device__ __forceinline__ float tagf(float v, uint32_t tag) { return __uint_as_float((__float_as_uint(v) & ~1u) | tag); }
__device__ __forceinline__ float untag(float v) { return __uint_as_float(__float_as_uint(v) & ~1u); }
__device__ __forceinline__ void st_x2(float2* p, float a, float b) { asm volatile("st.relaxed.gpu.global.v2.f32 [%0], {%1,%2};" ::"l"(p), "f"(a), "f"(b) : "memory"); }
__device__ __forceinline__ float2 ld_x2(const float2* p) { float2 v; asm volatile("ld.relaxed.gpu.global.v2.f32 {%0,%1}, [%2];" : "=f"(v.x), "=f"(v.y) : "l"(p) : "memory"); return v; }
__device__ __forceinline__ void st_u2(uint2* p, uint32_t a, uint32_t b) { asm volatile("st.relaxed.gpu.global.v2.u32 [%0], {%1,%2};" ::"l"(p), "r"(a), "r"(b) : "memory"); }
__device__ __forceinline__ void prefetch2d(const CUtensorMap* m, int c0, int c1) { asm volatile("cp.async.bulk.prefetch.tensor.2d.L2.global [%0, {%1, %2}];" ::"l"(m), "r"(c0), "r"(c1) : "memory"); }
__device__ __forceinline__ void prefetch1d(const void* p, uint32_t bytes) { asm volatile("cp.async.bulk.prefetch.L2.global [%0], %1;" ::"l"(p), "r"(bytes) : "memory"); }
__device__ __forceinline__ uint32_t ld_x1(const void* p) { uint32_t v; asm volatile("ld.relaxed.gpu.global.u32 %0, [%1];" : "=r"(v) : "l"(p) : "memory"); return v; }
__device__ __forceinline__ uint4 ld_x4(const void* p) { uint4 v; asm volatile("ld.relaxed.gpu.global.v4.u32 {%0,%1,%2,%3}, [%4];" : "=r"(v.x), "=r"(v.y), "=r"(v.z), "=r"(v.w) : "l"(p) : "memory"); return v; }
__device__ __forceinline__ void st_x4(void* p, uint32_t a, uint32_t b, uint32_t c, uint32_t d) { asm volatile("st.relaxed.gpu.global.v4.u32 [%0], {%1,%2,%3,%4};" ::"l"(p), "r"(a), "r"(b), "r"(c), "r"(d) : "memory"); }
__device__ __forceinline__ uint32_t mapa(uint32_t a, uint32_t cta) { uint32_t r; asm volatile("mapa.shared::cluster.u32 %0, %1, %2;" : "=r"(r) : "r"(a), "r"(cta)); return r; }
__device__ __forceinline__ void hint_add(unsigned* p) { asm volatile("red.relaxed.gpu.global.add.u32 [%0], 1;" ::"l"(p) : "memory"); }
__device__ __forceinline__ void hint_wait(const unsigned* p, unsigned target) {
  const uint32_t t0 = (uint32_t)clock();
  while ((int)(ld_x1(p) - target) < 0) spin_guard(t0);
}
__device__ __forceinline__ void load32_tagged(float2 (&v)[32], const float2* src, int stride, uint32_t tag) {
  const uint32_t t0 = (uint32_t)clock();
  for (;;) {
    uint32_t bad = 0;
#pragma unroll
    for (int a = 0; a < 32; a++) v[a] = ld_x2(src + a * stride);
#pragma unroll
    for (int a = 0; a < 32; a++) bad |= __float_as_uint(v[a].x) ^ tag;
    if (!__any_sync(0xffffffffu, bad & 1)) break;
    spin_guard(t0);
  }
#pragma unroll
  for (int a = 0; a < 32; a++) v[a].x = untag(v[a].x);
}
__device__ __forceinline__ void tma2d(uint32_t dst, const CUtensorMap* m, uint32_t bar, int c0, int c1) {
  asm volatile("cp.async.bulk.tensor.2d.shared::cluster.global.mbarrier::complete_tx::bytes [%0], [%1, {%3, %4}], [%2];" ::"r"(dst), "l"(m), "r"(bar), "r"(c0), "r"(c1) : "memory");
}
__device__ __forceinline__ void tma3d(uint32_t dst, const CUtensorMap* m, uint32_t bar, int c0, int c1, int c2) {
  asm volatile("cp.async.bulk.tensor.3d.shared::cluster.global.mbarrier::complete_tx::bytes [%0], [%1, {%3, %4, %5}], [%2];" ::"r"(dst), "l"(m), "r"(bar), "r"(c0), "r"(c1), "r"(c2) : "memory");
}
__device__ __forceinline__ void tma4d(uint32_t dst, const CUtensorMap* m, uint32_t bar, int c0, int c1, int c2, int c3) {
  asm volatile("cp.async.bulk.tensor.4d.shared::cluster.global.mbarrier::complete_tx::bytes [%0], [%1, {%3, %4, %5, %6}], [%2];" ::"r"(dst), "l"(m), "r"(bar), "r"(c0), "r"(c1), "r"(c2), "r"(c3) : "memory");
}
__device__ __forceinline__ void wg_fence() { asm volatile("wgmma.fence.sync.aligned;" ::: "memory"); }
__device__ __forceinline__ void wg_commit() { asm volatile("wgmma.commit_group.sync.aligned;" ::: "memory"); }
template <int N> __device__ __forceinline__ void wg_wait() { asm volatile("wgmma.wait_group.sync.aligned %0;" ::"n"(N) : "memory"); }
template <int O, int N, int NN> __device__ __forceinline__ void fence_regs(float (&d)[NN]) {
#pragma unroll
  for (int i = 0; i < N; i++) asm volatile("" : "+f"(d[O + i])::"memory");
}
__device__ __forceinline__ uint32_t pack_bf16(float lo, float hi) {
  uint32_t r; asm("cvt.rn.bf16x2.f32 %0, %1, %2;" : "=r"(r) : "f"(hi), "f"(lo)); return r;
}
__device__ __forceinline__ uint32_t pack_pin(float lo, float hi) {
  uint32_t r; asm volatile("cvt.rn.bf16x2.f32 %0, %1, %2;" : "=r"(r) : "f"(hi), "f"(lo) : "memory"); return r;
}
__device__ __forceinline__ float bf_lo(uint32_t u) { return __uint_as_float(u << 16); }
__device__ __forceinline__ float bf_hi(uint32_t u) { return __uint_as_float(u & 0xffff0000u); }

__device__ __forceinline__ uint64_t d128(uint32_t lo) { uint64_t d; asm("mov.b64 %0, {%1, 0x40000040};" : "=l"(d) : "r"(lo)); return d; }
__device__ __forceinline__ uint64_t d64(uint32_t lo) { uint64_t d; asm("mov.b64 %0, {%1, 0x80000020};" : "=l"(d) : "r"(lo)); return d; }
template<int O,int TB,int ACC,int NN> __device__ __forceinline__ void mma_ss64(float (&d)[NN], uint64_t da, uint64_t db, int sd = 0){
  if constexpr (ACC == 1) asm volatile("wgmma.mma_async.sync.aligned.m64n64k16.f32.bf16.bf16 {%0,%1,%2,%3,%4,%5,%6,%7,%8,%9,%10,%11,%12,%13,%14,%15,%16,%17,%18,%19,%20,%21,%22,%23,%24,%25,%26,%27,%28,%29,%30,%31}, %32, %33, 1, 1, 1, 0, %34;"
   : "+f"(d[O+0]), "+f"(d[O+1]), "+f"(d[O+2]), "+f"(d[O+3]), "+f"(d[O+4]), "+f"(d[O+5]), "+f"(d[O+6]), "+f"(d[O+7]), "+f"(d[O+8]), "+f"(d[O+9]), "+f"(d[O+10]), "+f"(d[O+11]), "+f"(d[O+12]), "+f"(d[O+13]), "+f"(d[O+14]), "+f"(d[O+15]), "+f"(d[O+16]), "+f"(d[O+17]), "+f"(d[O+18]), "+f"(d[O+19]), "+f"(d[O+20]), "+f"(d[O+21]), "+f"(d[O+22]), "+f"(d[O+23]), "+f"(d[O+24]), "+f"(d[O+25]), "+f"(d[O+26]), "+f"(d[O+27]), "+f"(d[O+28]), "+f"(d[O+29]), "+f"(d[O+30]), "+f"(d[O+31])
   : "l"(da), "l"(db), "n"(TB));
  else if constexpr (ACC == 0) asm volatile("wgmma.mma_async.sync.aligned.m64n64k16.f32.bf16.bf16 {%0,%1,%2,%3,%4,%5,%6,%7,%8,%9,%10,%11,%12,%13,%14,%15,%16,%17,%18,%19,%20,%21,%22,%23,%24,%25,%26,%27,%28,%29,%30,%31}, %32, %33, 0, 1, 1, 0, %34;"
   : "=f"(d[O+0]), "=f"(d[O+1]), "=f"(d[O+2]), "=f"(d[O+3]), "=f"(d[O+4]), "=f"(d[O+5]), "=f"(d[O+6]), "=f"(d[O+7]), "=f"(d[O+8]), "=f"(d[O+9]), "=f"(d[O+10]), "=f"(d[O+11]), "=f"(d[O+12]), "=f"(d[O+13]), "=f"(d[O+14]), "=f"(d[O+15]), "=f"(d[O+16]), "=f"(d[O+17]), "=f"(d[O+18]), "=f"(d[O+19]), "=f"(d[O+20]), "=f"(d[O+21]), "=f"(d[O+22]), "=f"(d[O+23]), "=f"(d[O+24]), "=f"(d[O+25]), "=f"(d[O+26]), "=f"(d[O+27]), "=f"(d[O+28]), "=f"(d[O+29]), "=f"(d[O+30]), "=f"(d[O+31])
   : "l"(da), "l"(db), "n"(TB));
  else asm volatile("{\n.reg .pred p;\nsetp.ne.b32 p, %35, 0;\nwgmma.mma_async.sync.aligned.m64n64k16.f32.bf16.bf16 {%0,%1,%2,%3,%4,%5,%6,%7,%8,%9,%10,%11,%12,%13,%14,%15,%16,%17,%18,%19,%20,%21,%22,%23,%24,%25,%26,%27,%28,%29,%30,%31}, %32, %33, p, 1, 1, 0, %34;\n}"
   : "+f"(d[O+0]), "+f"(d[O+1]), "+f"(d[O+2]), "+f"(d[O+3]), "+f"(d[O+4]), "+f"(d[O+5]), "+f"(d[O+6]), "+f"(d[O+7]), "+f"(d[O+8]), "+f"(d[O+9]), "+f"(d[O+10]), "+f"(d[O+11]), "+f"(d[O+12]), "+f"(d[O+13]), "+f"(d[O+14]), "+f"(d[O+15]), "+f"(d[O+16]), "+f"(d[O+17]), "+f"(d[O+18]), "+f"(d[O+19]), "+f"(d[O+20]), "+f"(d[O+21]), "+f"(d[O+22]), "+f"(d[O+23]), "+f"(d[O+24]), "+f"(d[O+25]), "+f"(d[O+26]), "+f"(d[O+27]), "+f"(d[O+28]), "+f"(d[O+29]), "+f"(d[O+30]), "+f"(d[O+31])
   : "l"(da), "l"(db), "n"(TB), "r"(sd));
}
template<int O,int TB,int ACC,int NN> __device__ __forceinline__ void mma_rs64(float (&d)[NN], uint32_t a0, uint32_t a1, uint32_t a2, uint32_t a3, uint64_t db, int sd = 0){
  if constexpr (ACC == 1) asm volatile("wgmma.mma_async.sync.aligned.m64n64k16.f32.bf16.bf16 {%0,%1,%2,%3,%4,%5,%6,%7,%8,%9,%10,%11,%12,%13,%14,%15,%16,%17,%18,%19,%20,%21,%22,%23,%24,%25,%26,%27,%28,%29,%30,%31}, {%32,%33,%34,%35}, %36, 1, 1, 1, %37;"
   : "+f"(d[O+0]), "+f"(d[O+1]), "+f"(d[O+2]), "+f"(d[O+3]), "+f"(d[O+4]), "+f"(d[O+5]), "+f"(d[O+6]), "+f"(d[O+7]), "+f"(d[O+8]), "+f"(d[O+9]), "+f"(d[O+10]), "+f"(d[O+11]), "+f"(d[O+12]), "+f"(d[O+13]), "+f"(d[O+14]), "+f"(d[O+15]), "+f"(d[O+16]), "+f"(d[O+17]), "+f"(d[O+18]), "+f"(d[O+19]), "+f"(d[O+20]), "+f"(d[O+21]), "+f"(d[O+22]), "+f"(d[O+23]), "+f"(d[O+24]), "+f"(d[O+25]), "+f"(d[O+26]), "+f"(d[O+27]), "+f"(d[O+28]), "+f"(d[O+29]), "+f"(d[O+30]), "+f"(d[O+31])
   : "r"(a0), "r"(a1), "r"(a2), "r"(a3), "l"(db), "n"(TB));
  else if constexpr (ACC == 0) asm volatile("wgmma.mma_async.sync.aligned.m64n64k16.f32.bf16.bf16 {%0,%1,%2,%3,%4,%5,%6,%7,%8,%9,%10,%11,%12,%13,%14,%15,%16,%17,%18,%19,%20,%21,%22,%23,%24,%25,%26,%27,%28,%29,%30,%31}, {%32,%33,%34,%35}, %36, 0, 1, 1, %37;"
   : "=f"(d[O+0]), "=f"(d[O+1]), "=f"(d[O+2]), "=f"(d[O+3]), "=f"(d[O+4]), "=f"(d[O+5]), "=f"(d[O+6]), "=f"(d[O+7]), "=f"(d[O+8]), "=f"(d[O+9]), "=f"(d[O+10]), "=f"(d[O+11]), "=f"(d[O+12]), "=f"(d[O+13]), "=f"(d[O+14]), "=f"(d[O+15]), "=f"(d[O+16]), "=f"(d[O+17]), "=f"(d[O+18]), "=f"(d[O+19]), "=f"(d[O+20]), "=f"(d[O+21]), "=f"(d[O+22]), "=f"(d[O+23]), "=f"(d[O+24]), "=f"(d[O+25]), "=f"(d[O+26]), "=f"(d[O+27]), "=f"(d[O+28]), "=f"(d[O+29]), "=f"(d[O+30]), "=f"(d[O+31])
   : "r"(a0), "r"(a1), "r"(a2), "r"(a3), "l"(db), "n"(TB));
  else asm volatile("{\n.reg .pred p;\nsetp.ne.b32 p, %38, 0;\nwgmma.mma_async.sync.aligned.m64n64k16.f32.bf16.bf16 {%0,%1,%2,%3,%4,%5,%6,%7,%8,%9,%10,%11,%12,%13,%14,%15,%16,%17,%18,%19,%20,%21,%22,%23,%24,%25,%26,%27,%28,%29,%30,%31}, {%32,%33,%34,%35}, %36, p, 1, 1, %37;\n}"
   : "+f"(d[O+0]), "+f"(d[O+1]), "+f"(d[O+2]), "+f"(d[O+3]), "+f"(d[O+4]), "+f"(d[O+5]), "+f"(d[O+6]), "+f"(d[O+7]), "+f"(d[O+8]), "+f"(d[O+9]), "+f"(d[O+10]), "+f"(d[O+11]), "+f"(d[O+12]), "+f"(d[O+13]), "+f"(d[O+14]), "+f"(d[O+15]), "+f"(d[O+16]), "+f"(d[O+17]), "+f"(d[O+18]), "+f"(d[O+19]), "+f"(d[O+20]), "+f"(d[O+21]), "+f"(d[O+22]), "+f"(d[O+23]), "+f"(d[O+24]), "+f"(d[O+25]), "+f"(d[O+26]), "+f"(d[O+27]), "+f"(d[O+28]), "+f"(d[O+29]), "+f"(d[O+30]), "+f"(d[O+31])
   : "r"(a0), "r"(a1), "r"(a2), "r"(a3), "l"(db), "n"(TB), "r"(sd));
}
template<int O,int TB,int ACC,int NN> __device__ __forceinline__ void mma_ss128(float (&d)[NN], uint64_t da, uint64_t db, int sd = 0){
  if constexpr (ACC == 1) asm volatile("wgmma.mma_async.sync.aligned.m64n128k16.f32.bf16.bf16 {%0,%1,%2,%3,%4,%5,%6,%7,%8,%9,%10,%11,%12,%13,%14,%15,%16,%17,%18,%19,%20,%21,%22,%23,%24,%25,%26,%27,%28,%29,%30,%31,%32,%33,%34,%35,%36,%37,%38,%39,%40,%41,%42,%43,%44,%45,%46,%47,%48,%49,%50,%51,%52,%53,%54,%55,%56,%57,%58,%59,%60,%61,%62,%63}, %64, %65, 1, 1, 1, 0, %66;"
   : "+f"(d[O+0]), "+f"(d[O+1]), "+f"(d[O+2]), "+f"(d[O+3]), "+f"(d[O+4]), "+f"(d[O+5]), "+f"(d[O+6]), "+f"(d[O+7]), "+f"(d[O+8]), "+f"(d[O+9]), "+f"(d[O+10]), "+f"(d[O+11]), "+f"(d[O+12]), "+f"(d[O+13]), "+f"(d[O+14]), "+f"(d[O+15]), "+f"(d[O+16]), "+f"(d[O+17]), "+f"(d[O+18]), "+f"(d[O+19]), "+f"(d[O+20]), "+f"(d[O+21]), "+f"(d[O+22]), "+f"(d[O+23]), "+f"(d[O+24]), "+f"(d[O+25]), "+f"(d[O+26]), "+f"(d[O+27]), "+f"(d[O+28]), "+f"(d[O+29]), "+f"(d[O+30]), "+f"(d[O+31]), "+f"(d[O+32]), "+f"(d[O+33]), "+f"(d[O+34]), "+f"(d[O+35]), "+f"(d[O+36]), "+f"(d[O+37]), "+f"(d[O+38]), "+f"(d[O+39]), "+f"(d[O+40]), "+f"(d[O+41]), "+f"(d[O+42]), "+f"(d[O+43]), "+f"(d[O+44]), "+f"(d[O+45]), "+f"(d[O+46]), "+f"(d[O+47]), "+f"(d[O+48]), "+f"(d[O+49]), "+f"(d[O+50]), "+f"(d[O+51]), "+f"(d[O+52]), "+f"(d[O+53]), "+f"(d[O+54]), "+f"(d[O+55]), "+f"(d[O+56]), "+f"(d[O+57]), "+f"(d[O+58]), "+f"(d[O+59]), "+f"(d[O+60]), "+f"(d[O+61]), "+f"(d[O+62]), "+f"(d[O+63])
   : "l"(da), "l"(db), "n"(TB));
  else if constexpr (ACC == 0) asm volatile("wgmma.mma_async.sync.aligned.m64n128k16.f32.bf16.bf16 {%0,%1,%2,%3,%4,%5,%6,%7,%8,%9,%10,%11,%12,%13,%14,%15,%16,%17,%18,%19,%20,%21,%22,%23,%24,%25,%26,%27,%28,%29,%30,%31,%32,%33,%34,%35,%36,%37,%38,%39,%40,%41,%42,%43,%44,%45,%46,%47,%48,%49,%50,%51,%52,%53,%54,%55,%56,%57,%58,%59,%60,%61,%62,%63}, %64, %65, 0, 1, 1, 0, %66;"
   : "=f"(d[O+0]), "=f"(d[O+1]), "=f"(d[O+2]), "=f"(d[O+3]), "=f"(d[O+4]), "=f"(d[O+5]), "=f"(d[O+6]), "=f"(d[O+7]), "=f"(d[O+8]), "=f"(d[O+9]), "=f"(d[O+10]), "=f"(d[O+11]), "=f"(d[O+12]), "=f"(d[O+13]), "=f"(d[O+14]), "=f"(d[O+15]), "=f"(d[O+16]), "=f"(d[O+17]), "=f"(d[O+18]), "=f"(d[O+19]), "=f"(d[O+20]), "=f"(d[O+21]), "=f"(d[O+22]), "=f"(d[O+23]), "=f"(d[O+24]), "=f"(d[O+25]), "=f"(d[O+26]), "=f"(d[O+27]), "=f"(d[O+28]), "=f"(d[O+29]), "=f"(d[O+30]), "=f"(d[O+31]), "=f"(d[O+32]), "=f"(d[O+33]), "=f"(d[O+34]), "=f"(d[O+35]), "=f"(d[O+36]), "=f"(d[O+37]), "=f"(d[O+38]), "=f"(d[O+39]), "=f"(d[O+40]), "=f"(d[O+41]), "=f"(d[O+42]), "=f"(d[O+43]), "=f"(d[O+44]), "=f"(d[O+45]), "=f"(d[O+46]), "=f"(d[O+47]), "=f"(d[O+48]), "=f"(d[O+49]), "=f"(d[O+50]), "=f"(d[O+51]), "=f"(d[O+52]), "=f"(d[O+53]), "=f"(d[O+54]), "=f"(d[O+55]), "=f"(d[O+56]), "=f"(d[O+57]), "=f"(d[O+58]), "=f"(d[O+59]), "=f"(d[O+60]), "=f"(d[O+61]), "=f"(d[O+62]), "=f"(d[O+63])
   : "l"(da), "l"(db), "n"(TB));
  else asm volatile("{\n.reg .pred p;\nsetp.ne.b32 p, %67, 0;\nwgmma.mma_async.sync.aligned.m64n128k16.f32.bf16.bf16 {%0,%1,%2,%3,%4,%5,%6,%7,%8,%9,%10,%11,%12,%13,%14,%15,%16,%17,%18,%19,%20,%21,%22,%23,%24,%25,%26,%27,%28,%29,%30,%31,%32,%33,%34,%35,%36,%37,%38,%39,%40,%41,%42,%43,%44,%45,%46,%47,%48,%49,%50,%51,%52,%53,%54,%55,%56,%57,%58,%59,%60,%61,%62,%63}, %64, %65, p, 1, 1, 0, %66;\n}"
   : "+f"(d[O+0]), "+f"(d[O+1]), "+f"(d[O+2]), "+f"(d[O+3]), "+f"(d[O+4]), "+f"(d[O+5]), "+f"(d[O+6]), "+f"(d[O+7]), "+f"(d[O+8]), "+f"(d[O+9]), "+f"(d[O+10]), "+f"(d[O+11]), "+f"(d[O+12]), "+f"(d[O+13]), "+f"(d[O+14]), "+f"(d[O+15]), "+f"(d[O+16]), "+f"(d[O+17]), "+f"(d[O+18]), "+f"(d[O+19]), "+f"(d[O+20]), "+f"(d[O+21]), "+f"(d[O+22]), "+f"(d[O+23]), "+f"(d[O+24]), "+f"(d[O+25]), "+f"(d[O+26]), "+f"(d[O+27]), "+f"(d[O+28]), "+f"(d[O+29]), "+f"(d[O+30]), "+f"(d[O+31]), "+f"(d[O+32]), "+f"(d[O+33]), "+f"(d[O+34]), "+f"(d[O+35]), "+f"(d[O+36]), "+f"(d[O+37]), "+f"(d[O+38]), "+f"(d[O+39]), "+f"(d[O+40]), "+f"(d[O+41]), "+f"(d[O+42]), "+f"(d[O+43]), "+f"(d[O+44]), "+f"(d[O+45]), "+f"(d[O+46]), "+f"(d[O+47]), "+f"(d[O+48]), "+f"(d[O+49]), "+f"(d[O+50]), "+f"(d[O+51]), "+f"(d[O+52]), "+f"(d[O+53]), "+f"(d[O+54]), "+f"(d[O+55]), "+f"(d[O+56]), "+f"(d[O+57]), "+f"(d[O+58]), "+f"(d[O+59]), "+f"(d[O+60]), "+f"(d[O+61]), "+f"(d[O+62]), "+f"(d[O+63])
   : "l"(da), "l"(db), "n"(TB), "r"(sd));
}
template<int O,int TB,int ACC,int NN> __device__ __forceinline__ void mma_rs128(float (&d)[NN], uint32_t a0, uint32_t a1, uint32_t a2, uint32_t a3, uint64_t db, int sd = 0){
  if constexpr (ACC == 1) asm volatile("wgmma.mma_async.sync.aligned.m64n128k16.f32.bf16.bf16 {%0,%1,%2,%3,%4,%5,%6,%7,%8,%9,%10,%11,%12,%13,%14,%15,%16,%17,%18,%19,%20,%21,%22,%23,%24,%25,%26,%27,%28,%29,%30,%31,%32,%33,%34,%35,%36,%37,%38,%39,%40,%41,%42,%43,%44,%45,%46,%47,%48,%49,%50,%51,%52,%53,%54,%55,%56,%57,%58,%59,%60,%61,%62,%63}, {%64,%65,%66,%67}, %68, 1, 1, 1, %69;"
   : "+f"(d[O+0]), "+f"(d[O+1]), "+f"(d[O+2]), "+f"(d[O+3]), "+f"(d[O+4]), "+f"(d[O+5]), "+f"(d[O+6]), "+f"(d[O+7]), "+f"(d[O+8]), "+f"(d[O+9]), "+f"(d[O+10]), "+f"(d[O+11]), "+f"(d[O+12]), "+f"(d[O+13]), "+f"(d[O+14]), "+f"(d[O+15]), "+f"(d[O+16]), "+f"(d[O+17]), "+f"(d[O+18]), "+f"(d[O+19]), "+f"(d[O+20]), "+f"(d[O+21]), "+f"(d[O+22]), "+f"(d[O+23]), "+f"(d[O+24]), "+f"(d[O+25]), "+f"(d[O+26]), "+f"(d[O+27]), "+f"(d[O+28]), "+f"(d[O+29]), "+f"(d[O+30]), "+f"(d[O+31]), "+f"(d[O+32]), "+f"(d[O+33]), "+f"(d[O+34]), "+f"(d[O+35]), "+f"(d[O+36]), "+f"(d[O+37]), "+f"(d[O+38]), "+f"(d[O+39]), "+f"(d[O+40]), "+f"(d[O+41]), "+f"(d[O+42]), "+f"(d[O+43]), "+f"(d[O+44]), "+f"(d[O+45]), "+f"(d[O+46]), "+f"(d[O+47]), "+f"(d[O+48]), "+f"(d[O+49]), "+f"(d[O+50]), "+f"(d[O+51]), "+f"(d[O+52]), "+f"(d[O+53]), "+f"(d[O+54]), "+f"(d[O+55]), "+f"(d[O+56]), "+f"(d[O+57]), "+f"(d[O+58]), "+f"(d[O+59]), "+f"(d[O+60]), "+f"(d[O+61]), "+f"(d[O+62]), "+f"(d[O+63])
   : "r"(a0), "r"(a1), "r"(a2), "r"(a3), "l"(db), "n"(TB));
  else if constexpr (ACC == 0) asm volatile("wgmma.mma_async.sync.aligned.m64n128k16.f32.bf16.bf16 {%0,%1,%2,%3,%4,%5,%6,%7,%8,%9,%10,%11,%12,%13,%14,%15,%16,%17,%18,%19,%20,%21,%22,%23,%24,%25,%26,%27,%28,%29,%30,%31,%32,%33,%34,%35,%36,%37,%38,%39,%40,%41,%42,%43,%44,%45,%46,%47,%48,%49,%50,%51,%52,%53,%54,%55,%56,%57,%58,%59,%60,%61,%62,%63}, {%64,%65,%66,%67}, %68, 0, 1, 1, %69;"
   : "=f"(d[O+0]), "=f"(d[O+1]), "=f"(d[O+2]), "=f"(d[O+3]), "=f"(d[O+4]), "=f"(d[O+5]), "=f"(d[O+6]), "=f"(d[O+7]), "=f"(d[O+8]), "=f"(d[O+9]), "=f"(d[O+10]), "=f"(d[O+11]), "=f"(d[O+12]), "=f"(d[O+13]), "=f"(d[O+14]), "=f"(d[O+15]), "=f"(d[O+16]), "=f"(d[O+17]), "=f"(d[O+18]), "=f"(d[O+19]), "=f"(d[O+20]), "=f"(d[O+21]), "=f"(d[O+22]), "=f"(d[O+23]), "=f"(d[O+24]), "=f"(d[O+25]), "=f"(d[O+26]), "=f"(d[O+27]), "=f"(d[O+28]), "=f"(d[O+29]), "=f"(d[O+30]), "=f"(d[O+31]), "=f"(d[O+32]), "=f"(d[O+33]), "=f"(d[O+34]), "=f"(d[O+35]), "=f"(d[O+36]), "=f"(d[O+37]), "=f"(d[O+38]), "=f"(d[O+39]), "=f"(d[O+40]), "=f"(d[O+41]), "=f"(d[O+42]), "=f"(d[O+43]), "=f"(d[O+44]), "=f"(d[O+45]), "=f"(d[O+46]), "=f"(d[O+47]), "=f"(d[O+48]), "=f"(d[O+49]), "=f"(d[O+50]), "=f"(d[O+51]), "=f"(d[O+52]), "=f"(d[O+53]), "=f"(d[O+54]), "=f"(d[O+55]), "=f"(d[O+56]), "=f"(d[O+57]), "=f"(d[O+58]), "=f"(d[O+59]), "=f"(d[O+60]), "=f"(d[O+61]), "=f"(d[O+62]), "=f"(d[O+63])
   : "r"(a0), "r"(a1), "r"(a2), "r"(a3), "l"(db), "n"(TB));
  else asm volatile("{\n.reg .pred p;\nsetp.ne.b32 p, %70, 0;\nwgmma.mma_async.sync.aligned.m64n128k16.f32.bf16.bf16 {%0,%1,%2,%3,%4,%5,%6,%7,%8,%9,%10,%11,%12,%13,%14,%15,%16,%17,%18,%19,%20,%21,%22,%23,%24,%25,%26,%27,%28,%29,%30,%31,%32,%33,%34,%35,%36,%37,%38,%39,%40,%41,%42,%43,%44,%45,%46,%47,%48,%49,%50,%51,%52,%53,%54,%55,%56,%57,%58,%59,%60,%61,%62,%63}, {%64,%65,%66,%67}, %68, p, 1, 1, %69;\n}"
   : "+f"(d[O+0]), "+f"(d[O+1]), "+f"(d[O+2]), "+f"(d[O+3]), "+f"(d[O+4]), "+f"(d[O+5]), "+f"(d[O+6]), "+f"(d[O+7]), "+f"(d[O+8]), "+f"(d[O+9]), "+f"(d[O+10]), "+f"(d[O+11]), "+f"(d[O+12]), "+f"(d[O+13]), "+f"(d[O+14]), "+f"(d[O+15]), "+f"(d[O+16]), "+f"(d[O+17]), "+f"(d[O+18]), "+f"(d[O+19]), "+f"(d[O+20]), "+f"(d[O+21]), "+f"(d[O+22]), "+f"(d[O+23]), "+f"(d[O+24]), "+f"(d[O+25]), "+f"(d[O+26]), "+f"(d[O+27]), "+f"(d[O+28]), "+f"(d[O+29]), "+f"(d[O+30]), "+f"(d[O+31]), "+f"(d[O+32]), "+f"(d[O+33]), "+f"(d[O+34]), "+f"(d[O+35]), "+f"(d[O+36]), "+f"(d[O+37]), "+f"(d[O+38]), "+f"(d[O+39]), "+f"(d[O+40]), "+f"(d[O+41]), "+f"(d[O+42]), "+f"(d[O+43]), "+f"(d[O+44]), "+f"(d[O+45]), "+f"(d[O+46]), "+f"(d[O+47]), "+f"(d[O+48]), "+f"(d[O+49]), "+f"(d[O+50]), "+f"(d[O+51]), "+f"(d[O+52]), "+f"(d[O+53]), "+f"(d[O+54]), "+f"(d[O+55]), "+f"(d[O+56]), "+f"(d[O+57]), "+f"(d[O+58]), "+f"(d[O+59]), "+f"(d[O+60]), "+f"(d[O+61]), "+f"(d[O+62]), "+f"(d[O+63])
   : "r"(a0), "r"(a1), "r"(a2), "r"(a3), "l"(db), "n"(TB), "r"(sd));
}

__host__ __device__ constexpr int brev(int a, int bits) { int r = 0; for (int i = 0; i < bits; i++) r |= ((a >> i) & 1) << (bits - 1 - i); return r; }
__host__ __device__ constexpr int ilog2(int n) { return n <= 1 ? 0 : 1 + ilog2(n / 2); }
template <int SG, int A> __device__ __forceinline__ void bfly(float2& a, float2& b) {
  if constexpr (A == 0) {
    float tr = a.x - b.x, ti = a.y - b.y; a.x += b.x; a.y += b.y; b.x = tr; b.y = ti;
  } else if constexpr (A == 8) {
    float pr = SG > 0 ? -b.y : b.y, pi = SG > 0 ? b.x : -b.x;
    b.x = a.x - pr; b.y = a.y - pi; a.x += pr; a.y += pi;
  } else {
    constexpr float wr = tbl::W32<A>::c, wi = SG * tbl::W32<A>::s;
    float tr = fmaf(wr, b.x, a.x), ti = fmaf(wr, b.y, a.y);
    tr = fmaf(-wi, b.y, tr); ti = fmaf(wi, b.x, ti);
    b.x = fmaf(2.f, a.x, -tr); b.y = fmaf(2.f, a.y, -ti); a.x = tr; a.y = ti;
  }
}
template <int SG, int N, int O, int ST, int A> __device__ __forceinline__ void dft_comb(float2 (&x)[32]) {
  if constexpr (A < N / 2) {
    constexpr int p = O + 2 * ST * brev(A, ilog2(N / 2));
    bfly<SG, A * (32 / N)>(x[p], x[p + ST]);
    dft_comb<SG, N, O, ST, A + 1>(x);
  }
}
template <int SG, int N, int O, int ST> __device__ __forceinline__ void dft(float2 (&x)[32]) {
  if constexpr (N > 1) {
    dft<SG, N / 2, O, 2 * ST>(x);
    dft<SG, N / 2, O + ST, 2 * ST>(x);
    dft_comb<SG, N, O, ST, 0>(x);
  }
}

#define TPACE 40
#define PFMODE 0
#define MAPMODE 0
template <int V> struct IC { static constexpr int value = V; };
struct Maps { CUtensorMap x, ft, g32, u32, g64, u64, e, wr, wi, d192, d32, fg; };

constexpr int NCTA = 132;
constexpr int U = 16384;
constexpr int TB = 36864;
constexpr int OFF_RING = 8 * U, OFF_Z = 9 * U, OFF_WRAW = 12 * U, OFF_T = 13 * U;
constexpr int OFF_BAR = 14 * U;
constexpr int SMEM_BYTES = OFF_BAR + 512;
constexpr int B_FX = 0, B_FA = 8, B_FT = 12, B_Z = 16, B_W = 20, B_HX = 21, B_HT = 22, B_HP = 23;
constexpr int B_EA = 26, B_ET = 30, B_RDY = 34;
constexpr int B_T = 35, NBAR = 36;

__global__ void __cluster_dims__(2, 1, 1) __launch_bounds__(512, 1)
fused_kernel(const __grid_constant__ Maps maps, const __nv_bfloat16* __restrict__ x, const __nv_bfloat16* __restrict__ w_r,
             const __nv_bfloat16* __restrict__ w_i, const __nv_bfloat16* __restrict__ gate_w, const __nv_bfloat16* __restrict__ Wd,
             __nv_bfloat16* __restrict__ out) {
  extern __shared__ __align__(1024) uint8_t smem[];
  const uint32_t sb = smem_u32(smem);
  const uint32_t bars = sb + OFF_BAR;
  const int tid = threadIdx.x, lane = tid & 31;
  const int warp = __shfl_sync(0xffffffffu, tid >> 5, 0);
  const bool helper = blockIdx.x >= 128;
  const int cl = (blockIdx.x >> 1) & 63, rank = blockIdx.x & 1;
  const int q4 = cl & 3, rb = cl >> 2;
  const int j = 2 * q4 + rank;
  const int f_full = 448 * q4 + (rank ? 256 : 0);
  const int f_half = 448 * q4 + (rank ? 224 : 192);
  const int kg = 2 * j + (rb >> 3), tn = rb & 7;

  if (tid == 64) { PROF_EV(0); PROF_CK(40); }
  auto ring_load = [&](int n) {
    const uint32_t fb = bars + 8 * (B_FA + (n & 3)), dst = sb + OFF_RING + (n & 3) * U;
    mbar_expect_tx(fb, U);
    if (n < 8) {
      tma2d(dst, &maps.ft, fb, 64 * n, 64 * j);
      tma2d(dst + 8192, &maps.g32, fb, f_half, 64 * n);
      tma2d(dst + 12288, &maps.u32, fb, f_half, 64 * n);
    } else if (n == 9 || n == 10 || n >= 34) {
      tma4d(dst, &maps.e, fb, 0, 0, 0, 2 * rb + (n >= 34 ? n - 34 : n - 9));
    } else {
      const int q = n == 8 ? 0 : n - 10;
      tma2d(dst, &maps.g64, fb, f_full + 64 * (q >> 3), 64 * (q & 7));
      tma2d(dst + 8192, &maps.u64, fb, f_full + 64 * (q >> 3), 64 * (q & 7));
    }
  };
  auto x_load = [&](int q) {
    mbar_expect_tx(bars + 8 * (B_FX + q), U);
    tma3d(sb + q * U, &maps.x, bars + 8 * (B_FX + q), 64 * q, 0, 2 * rb);
  };
  if (warp >= 12 && lane == 0) {
    if (warp < 14) {
      const int p = warp - 12;
      mbar_init(bars + 8 * (B_FX + p), 1); mbar_init(bars + 8 * (B_FA + p), 1);
      mbar_init(bars + 8 * (B_FX + p + 2), 1); mbar_init(bars + 8 * (B_FA + p + 2), 1);
      asm volatile("fence.proxy.async.shared::cta;" ::: "memory");
      if (!helper) { x_load(p); ring_load(p); }
    } else if (warp == 14) {
#pragma unroll
      for (int i = 4; i < 8; i++) mbar_init(bars + 8 * (B_FX + i), 1);
#pragma unroll
      for (int i = 4; i < 12; i++) asm volatile("prefetch.tensormap [%0];" ::"l"((const char*)&maps + i * 128) : "memory");
    } else {
#pragma unroll
      for (int i = B_FT; i < NBAR; i++) mbar_init(bars + 8 * i, i < B_EA ? 1 : i < B_T ? 2 : 4);
#pragma unroll
      for (int i = 0; i < 4; i++) mbar_expect_tx(bars + 8 * (B_Z + i), U);
      asm volatile("fence.mbarrier_init.release.cluster;" ::: "memory");
    }
  }
  __syncthreads();
  asm volatile("barrier.cluster.arrive.relaxed.aligned;" ::: "memory");
  if (tid == 64) PROF_EV(38);

  if (warp >= 12) {
    asm volatile("setmaxnreg.dec.sync.aligned.u32 24;");
    if (lane == 0 && !helper) {
      if (warp == 12) PROF_EV(30);
      if (warp < 14) {
#pragma unroll 1
        for (int n = warp - 10; n < 36; n += 2) {
          if (n >= 4) mbar_wait(bars + 8 * (B_EA + (n & 3)), ((n >> 2) & 1) ^ 1);
          else x_load(n);
          ring_load(n);
          if (n >= 3 && n < 7) x_load(n + 1);
        }
      } else if (warp == 15) {
        const unsigned ep1 = ld_x1(&g_epoch[blockIdx.x * 8]) + 1;
        hint_wait(&g_cntX[32 * j], ep1 * 128u); mbar_arrive(bars + 8 * B_HX);
        hint_wait(&g_cntT[32 * j], ep1 * (j == 0 ? 68u : 64u)); mbar_arrive(bars + 8 * B_HT);
#pragma unroll 1
        for (int i = 0; i < 3; i++) { hint_wait(&g_cntP[32 * (rb * 8 + j) + i], ep1 * 8u); mbar_arrive(bars + 8 * (B_HP + i)); }
      } else {
        PROF_EV(31);
        mbar_wait(bars + 8 * (B_FX + 7), 0);
        PROF_EV(32);
        mbar_expect_tx(bars + 8 * B_W, 24576);
        tma4d(sb + OFF_WRAW, &maps.wr, bars + 8 * B_W, 16 * kg, 0, tn, 0);
        tma4d(sb + OFF_WRAW + 12288, &maps.wi, bars + 8 * B_W, 16 * kg, 0, tn, 0);
#pragma unroll 1
        for (int t = 0; t < 8; t++) {
          const int i = t < 3 ? t + 1 : t < 6 ? t - 2 : 0;
          const int col = 64 * (2 * ((q4 + i) & 3) + ((t < 3 || t == 6) ? 1 - rank : rank));
          const uint32_t fb = bars + 8 * (B_FT + (t & 3)), dst = sb + (t & 3) * TB;
          mbar_wait(bars + 8 * (B_ET + (t & 3)), t >> 2);
          mbar_expect_tx(fb, TB);
          tma2d(dst, &maps.d192, fb, col, f_full);
          tma2d(dst + 24576, &maps.d32, fb, col, f_half);
          tma4d(dst + 28672, &maps.fg, fb, col, 0, 0, 4 * j);
        }
      }
    }
  } else if (warp >= 8) {
    asm volatile("setmaxnreg.dec.sync.aligned.u32 88;");
    const int t = tid - 256, w = warp - 8;
    const float scale = 2.0f / (2048.0f * 512.0f);
    const uint32_t ep = ld_x1(&g_epoch[blockIdx.x * 8]);
    if (!helper) {
      uint4 xv[8], gv[2];
#pragma unroll
      for (int i = 0; i < 4; i++) {
        const int r = 16 * j + 4 * w + i;
        const uint4* p = (const uint4*)(x + (size_t)(2 * rb + (r >> 6) + 32 * (r & 63)) * 512) + lane;
        xv[2 * i] = __ldg(p); xv[2 * i + 1] = __ldg(p + 32);
      }
      gv[0] = __ldg((const uint4*)gate_w + lane); gv[1] = __ldg((const uint4*)gate_w + lane + 32);
      const uint32_t tag = (ep + 1) & 1;
      {
        float z[4];
#pragma unroll
        for (int i = 0; i < 4; i++) {
          float a = 0.f;
#pragma unroll
          for (int hh = 0; hh < 2; hh++) {
            const uint4 u = xv[2 * i + hh], v = gv[hh];
            a = fmaf(bf_lo(u.x), bf_lo(v.x), a); a = fmaf(bf_hi(u.x), bf_hi(v.x), a);
            a = fmaf(bf_lo(u.y), bf_lo(v.y), a); a = fmaf(bf_hi(u.y), bf_hi(v.y), a);
            a = fmaf(bf_lo(u.z), bf_lo(v.z), a); a = fmaf(bf_hi(u.z), bf_hi(v.z), a);
            a = fmaf(bf_lo(u.w), bf_lo(v.w), a); a = fmaf(bf_hi(u.w), bf_hi(v.w), a);
          }
#pragma unroll
          for (int o = 16; o; o >>= 1) a += __shfl_xor_sync(0xffffffffu, a, o);
          z[i] = a;
        }
        if (lane < 4) {
          const float zz = lane == 0 ? z[0] : lane == 1 ? z[1] : lane == 2 ? z[2] : z[3];
          asm volatile("st.relaxed.gpu.global.f32 [%0], %1;" ::"l"(g_gate + rb * 128 + 16 * j + 4 * w + lane), "f"(tagf(1.0f / (1.0f + __expf(-zz)), tag)) : "memory");
        }
        if (t == 0) PROF_EV(18);
      }
      if (w == 0) {
        const int c = lane >> 4, jj = 16 * blockIdx.x + (lane & 15), jm = (2048 - jj) & 2047;
        const unsigned short* pr = (const unsigned short*)w_r + 256 * c;
        const unsigned short* pi = (const unsigned short*)w_i + 256 * c;
        const float wr = 0.5f * (bf_lo(__ldg(pr + jj * 257)) + bf_lo(__ldg(pr + jm * 257)));
        const float wi = 0.5f * (bf_lo(__ldg(pi + jj * 257)) - bf_lo(__ldg(pi + jm * 257)));
        st_x2(g_Wh + c * 2048 + jj, tagf(c ? -wi : wr, tag), c ? wr : wi);
        __syncwarp();
        if (lane == 0) hint_add(&g_cntW[0]);
      }
      const int k = 16 * kg + (t & 15), j1 = 8 * tn + (t >> 4);
      {
        const unsigned short* p = (const unsigned short*)(smem + OFF_WRAW) + (t >> 4) * 25 + (t & 15);
        uint32_t wv[32];
        mbar_wait(bars + 8 * B_W, 0);
#pragma unroll
        for (int a = 0; a < 32; a++) wv[a] = (uint32_t)p[a * 192] | ((uint32_t)p[6144 + a * 192] << 16);
        asm volatile("bar.sync 1, 128;" ::: "memory");
#pragma unroll
        for (int a = 0; a < 8; a++) *(uint4*)(smem + OFF_WRAW + (a * 128 + t) * 16) = make_uint4(wv[4 * a], wv[4 * a + 1], wv[4 * a + 2], wv[4 * a + 3]);
      }
      if (t == 0) PROF_EV(11);
      mbar_wait(bars + 8 * B_HX, 0);
      float2 v[32];
      if (t == 0) PROF_EV(22);
      {
        const uint32_t* src = (const uint32_t*)(g_X1p + (size_t)(kg * 8 + tn) * 2048 + ((t >> 3) & 1) * 32 + w * 8 + (t & 7)) + ((t >> 4) & 1);
        const uint32_t chk = (t & 16) ? 0u : 1u;
        uint32_t u[32];
        const uint32_t t0 = (uint32_t)clock();
        for (;;) {
          uint32_t bad = 0;
#pragma unroll
          for (int a = 0; a < 32; a++) u[a] = ld_x1(src + a * 128);
#pragma unroll
          for (int a = 0; a < 32; a++) bad |= u[a] ^ tag;
          if (!__any_sync(0xffffffffu, bad & chk)) break;
          spin_guard(t0);
        }
#pragma unroll
        for (int a = 0; a < 32; a++) v[a] = make_float2(bf_lo(u[a] & ~chk), bf_hi(u[a]));
      }
      if (t == 0) PROF_EV(12);
      dft<-1, 32, 0, 1>(v);
      float2 y[32];
#pragma unroll
      for (int a4 = 0; a4 < 8; a4++) {
        const uint4 ww = *(const uint4*)(smem + OFF_WRAW + (a4 * 128 + t) * 16);
        const uint32_t wq[4] = {ww.x, ww.y, ww.z, ww.w};
#pragma unroll
        for (int e = 0; e < 4; e++) {
          const float2 z = v[brev(4 * a4 + e, 5)];
          const float wr = bf_lo(wq[e]), wi = bf_hi(wq[e]);
          y[4 * a4 + e] = make_float2(fmaf(z.x, wr, -z.y * wi), fmaf(z.x, wi, z.y * wr));
        }
      }
      dft<1, 32, 0, 1>(y);
      if (t == 0) PROF_EV(16);
      {
        uint2* dst = g_T + (size_t)j * 32768 + (kg & 1) * 1024 + j1 * 16 + (t & 15);
#pragma unroll
        for (int a = 0; a < 16; a++) {
          const float2 u0 = y[brev(2 * a, 5)], u1 = y[brev(2 * a + 1, 5)];
          if (k != 0) st_u2(dst + a * 2048, (pack_bf16(u0.x * scale, u0.y * scale) & ~1u) | tag, pack_bf16(u1.x * scale, u1.y * scale));
          if (TPACE && (a & 3) == 3 && a < 15) __nanosleep(TPACE);
        }
        __syncwarp();
        if (lane == 0) hint_add(&g_cntT[32 * j]);
      }
      if (t == 0) PROF_EV(17);
      {
        const uint4* src = (const uint4*)(g_T + (size_t)(j * 16 + rb) * 2048) + t;
        uint4 u[8];
        mbar_wait(bars + 8 * B_HT, 0);
        if (t == 0) PROF_EV(23);
        const uint32_t t0 = (uint32_t)clock();
        for (;;) {
          uint32_t bad = 0;
#pragma unroll
          for (int a = 0; a < 8; a++) u[a] = ld_x4(src + a * 128);
#pragma unroll
          for (int a = 0; a < 8; a++) bad |= (u[a].x ^ tag) | (u[a].z ^ tag);
          if (!__any_sync(0xffffffffu, bad & 1)) break;
          spin_guard(t0);
        }
        const int r = t >> 3, c = t & 7;
#pragma unroll
        for (int a = 0; a < 8; a++) {
          const uint32_t dst = sb + OFF_T + (16 * (a & 3) + r) * 128 + ((((a >> 2) * 4 + (c >> 1)) ^ (r & 7)) << 4) + (c & 1) * 8;
          asm volatile("st.shared.v2.u32 [%0], {%1,%2};" ::"r"(dst), "r"(u[a].x & ~1u), "r"(u[a].z & ~1u) : "memory");
          asm volatile("st.shared.v2.u32 [%0], {%1,%2};" ::"r"(dst + 8192), "r"(u[a].y), "r"(u[a].w) : "memory");
        }
        asm volatile("fence.proxy.async.shared::cta;" ::: "memory");
        __syncwarp();
        if (lane == 0) mbar_arrive(bars + 8 * B_T);
        if (t == 0) PROF_EV(13);
      }
    } else if (w == 0) {
      const uint32_t tag = (ep + 1) & 1;
      const int c = lane >> 4, j1 = 16 * (blockIdx.x - 128) + (lane & 15);
      float2* wf = (float2*)smem;
      float2 v[32];
      hint_wait(&g_cntW[0], (ep + 1) * 128u);
      load32_tagged(v, g_Wh + c * 2048 + j1, 64, tag);
#pragma unroll
      for (int a = 0; a < 32; a++) wf[a * 32 + lane] = v[a];
      if (t == 0) PROF_EV(11);
      hint_wait(&g_cntX[0], (ep + 1) * 128u);
      load32_tagged(v, g_X1s + c * 2048 + j1, 64, tag);
      if (t == 0) PROF_EV(12);
      dft<-1, 32, 0, 1>(v);
      float2 y[32];
#pragma unroll
      for (int a = 0; a < 32; a++) {
        const float2 z = v[brev(a, 5)], wv = wf[a * 32 + lane];
        y[a] = make_float2(fmaf(z.x, wv.x, -z.y * wv.y), fmaf(z.x, wv.y, z.y * wv.x));
      }
      dft<1, 32, 0, 1>(y);
      if (t == 0) PROF_EV(16);
#pragma unroll
      for (int a = 0; a < 8; a++) {
        uint32_t pk[2];
#pragma unroll
        for (int e = 0; e < 2; e++) {
          const float2 u0 = y[brev(4 * a + e, 5)], u1 = y[brev(4 * a + 2 + e, 5)];
          const float2 keep = c ? u1 : u0, give = c ? u0 : u1;
          const float ox = __shfl_xor_sync(0xffffffffu, give.x, 16), oy = __shfl_xor_sync(0xffffffffu, give.y, 16);
          pk[e] = pack_bf16((keep.x + ox) * (0.5f * scale), (keep.y + oy) * (0.5f * scale));
        }
        st_u2(g_T + (2 * a + c) * 2048 + j1 * 16, (pk[0] & ~1u) | tag, pk[1]);
      }
      __syncwarp();
      if (t == 0) { hint_add(&g_cntT[0]); g_epoch[blockIdx.x * 8] = ep + 1; PROF_EV(13); }
    }
  } else {
    asm volatile("setmaxnreg.inc.sync.aligned.u32 200;");
    if (!helper) {
      const int wg = warp >> 2, w = warp & 3, g = lane >> 2, q = lane & 3;
      const bool elect = (tid & 127) == 0;
      const uint32_t ep = ld_x1(&g_epoch[blockIdx.x * 8]);
      float c1[64], cA[64], c2[64], ci[64], ct[64];
      const int zero = blockIdx.x >> 16;
      uint32_t h[56], yf[16];
      const uint32_t d0 = (sb & 0x3FFFF) >> 4;
      const uint32_t dK = d0 | (1u << 16), dN = d0 | (512u << 16), dM = d0 | (256u << 16);
      const uint32_t dX = dK + wg * 512;
      constexpr uint32_t RING = OFF_RING >> 4;
      auto waitA = [&](int n) { mbar_wait(bars + 8 * (B_FA + (n & 3)), (n >> 2) & 1); };
      auto freeA = [&](int n) { if (elect) mbar_arrive(bars + 8 * (B_EA + (n & 3))); };

      auto c1_step = [&](auto first, int kb) {
        mbar_wait(bars + 8 * (B_FX + kb), 0); waitA(kb);
        wg_fence();
        const uint64_t dx = d128(dX + kb * 1024), df = d128(dK + RING + (kb & 3) * 1024), dm = d64(dM + RING + 512 + (kb & 3) * 1024);
        mma_ss64<0, 0, decltype(first)::value>(c1, df, dx);
        mma_ss64<32, 1, decltype(first)::value>(c1, dx, dm);
#pragma unroll
        for (int k = 1; k < 4; k++) {
          mma_ss64<0, 0, 1>(c1, df + k * 2, dx + k * 2);
          mma_ss64<32, 1, 1>(c1, dx + k * 2, dm + k * 64);
        }
        wg_commit();
      };
      c1_step(IC<0>(), 0);
      if (tid == 0) PROF_EV(1);
#pragma unroll 1
      for (int kb = 1; kb < 8; kb++) { c1_step(IC<1>(), kb); wg_wait<1>(); freeA(kb - 1); }
      auto ffn_step = [&](auto first, float (&acc)[64], int n, int kb) {
        waitA(n);
        wg_fence();
        const uint64_t dx = d128(dX + kb * 1024), db = d128(dN + RING + (n & 3) * 1024);
        mma_ss128<0, 1, decltype(first)::value>(acc, dx, db, zero);
#pragma unroll
        for (int k = 1; k < 4; k++) mma_ss128<0, 1, 1>(acc, dx + k * 2, db + k * 128);
        wg_commit();
        wg_wait<1>();
      };
      const uint32_t tag = (ep + 1) & 1;
      const float* gp = g_gate + rb * 128 + wg * 64 + w * 16 + g;
      uint32_t gb0 = ld_x1(gp), gb1 = ld_x1(gp + 8);
      ffn_step(IC<0>(), c2, 8, 0);
      freeA(7);
      fence_regs<0, 64>(c1);
      if (tid == 0) PROF_EV(2);
#pragma unroll
      for (int i = 0; i < 16; i++) yf[i] = pack_pin(c1[2 * i], c1[2 * i + 1]);
      {
        const uint32_t t0 = (uint32_t)clock();
        while (__any_sync(0xffffffffu, ((gb0 ^ tag) | (gb1 ^ tag)) & 1)) { gb0 = ld_x1(gp); gb1 = ld_x1(gp + 8); spin_guard(t0); }
      }
      if (tid == 0) PROF_EV(10);
      const float g0 = __uint_as_float(gb0 & ~1u), g1 = __uint_as_float(gb1 & ~1u);
      const float o0 = 1.0f - g0, o1 = 1.0f - g1;
#pragma unroll
      for (int i = 0; i < 8; i++) {
        const float o = (i & 1) ? o1 : o0;
        h[48 + i] = pack_pin(fmaxf(c1[32 + 2 * i], 0.f) * c1[48 + 2 * i] * o, fmaxf(c1[33 + 2 * i], 0.f) * c1[49 + 2 * i] * o);
      }
      {
        waitA(9); waitA(10);
        const uint64_t de = d128(dN + RING + (1 + wg) * 1024);
        wg_fence();
        mma_rs128<0, 1, 0>(cA, yf[0], yf[1], yf[2], yf[3], de);
#pragma unroll
        for (int k = 1; k < 4; k++) mma_rs128<0, 1, 1>(cA, yf[4 * k], yf[4 * k + 1], yf[4 * k + 2], yf[4 * k + 3], de + k * 128);
        wg_commit();
        wg_wait<1>();
        freeA(8);
        ffn_step(IC<1>(), c2, 11, 1);
        freeA(9); freeA(10);
        fence_regs<0, 64>(cA);
        if (tid == 0) PROF_EV(19);
        const int s0 = 2 * rb + wg;
        uint2* dst = g_X1p + ((size_t)((2 * j + (w >> 1)) * 8) * 32 + s0) * 64 + (w & 1) * 32 + q * 8 + g;
        auto x1_store = [&](int n0, int n1) {
#pragma unroll
          for (int n = n0; n < n1; n++)
            st_u2(dst + n * 2048, (pack_bf16(cA[4 * n] - cA[34 + 4 * n], cA[32 + 4 * n] + cA[4 * n + 2]) & ~1u) | tag,
                  pack_bf16(cA[4 * n + 1] - cA[35 + 4 * n], cA[33 + 4 * n] + cA[4 * n + 3]));
        };
        if (j == 0 && w == 0 && g == 0) {
#pragma unroll
          for (int n = 0; n < 8; n++) {
#pragma unroll
            for (int e = 0; e < 2; e++) {
              st_x2(g_X1s + s0 * 64 + 8 * n + 2 * q + e, tagf(cA[4 * n + e], tag), cA[32 + 4 * n + e]);
              st_x2(g_X1s + (32 + s0) * 64 + 8 * n + 2 * q + e, tagf(cA[4 * n + 2 + e], tag), cA[34 + 4 * n + e]);
            }
          }
        }
        __syncwarp();
        x1_store(0, 3);
        ffn_step(IC<1>(), c2, 12, 2); freeA(11);
        x1_store(3, 6);
        ffn_step(IC<1>(), c2, 13, 3); freeA(12);
        x1_store(6, 8);
        __syncwarp();
        if (lane == 0) hint_add(&g_cntX[32 * j]);
        if (tid == 0) PROF_EV(3);
      }
      auto glu = [&](float (&acc)[64], int ho) {
#pragma unroll
        for (int i = 0; i < 16; i++) {
          const float o = (i & 1) ? o1 : o0;
          h[ho + i] = pack_pin(fmaxf(acc[2 * i], 0.f) * acc[32 + 2 * i] * o, fmaxf(acc[2 * i + 1], 0.f) * acc[33 + 2 * i] * o);
        }
      };
#pragma unroll 1
      for (int kb = 4; kb < 8; kb++) { ffn_step(IC<1>(), c2, 10 + kb, kb); freeA(9 + kb); }
      ffn_step(IC<2>(), cA, 18, 0); freeA(17);
      fence_regs<0, 64>(c2);
      if (tid == 0) PROF_EV(4);
      glu(c2, 0);
#pragma unroll 1
      for (int kb = 1; kb < 8; kb++) { ffn_step(IC<1>(), cA, 18 + kb, kb); freeA(17 + kb); }
      ffn_step(IC<2>(), c2, 26, 0); freeA(25);
      fence_regs<0, 64>(cA);
      if (tid == 0) PROF_EV(5);
      glu(cA, 16);
#pragma unroll 1
      for (int kb = 1; kb < 8; kb++) {
        ffn_step(IC<1>(), c2, 26 + kb, kb); freeA(25 + kb);
        if (elect && kb >= 3 && (kb & 1)) mbar_arrive(bars + 8 * (B_ET + ((kb - 3) >> 1)));
      }
      wg_wait<0>();
      if (elect) mbar_arrive(bars + 8 * (B_ET + 3));
      fence_regs<0, 64>(c2);
      glu(c2, 32);
      waitA(34 + wg);
      if (tid == 0) PROF_EV(6);
      mbar_wait(bars + 8 * B_T, 0);
      if (tid == 0) PROF_EV(7);
      wg_fence();
      {
        const uint64_t dt = d128(dN + (OFF_T >> 4) + wg * 512), de = d128(dK + RING + (2 + wg) * 1024);
        mma_ss64<0, 1, 0>(ci, de, dt);
        mma_ss64<32, 1, 0>(ci, de + 512, dt);
#pragma unroll
        for (int k = 1; k < 4; k++) {
          mma_ss64<0, 1, 1>(ci, de + k * 2, dt + k * 128);
          mma_ss64<32, 1, 1>(ci, de + (512 + k * 2), dt + k * 128);
        }
      }
      wg_commit();

      auto head = [&](auto off, int t) {
        constexpr int O = decltype(off)::value;
        mbar_wait(bars + 8 * (B_FT + (t & 3)), t >> 2);
        const uint64_t db = d128(dN + (t & 3) * (TB >> 4));
        wg_fence();
        mma_rs64<O, 1, 0>(ct, h[0], h[1], h[2], h[3], db);
#pragma unroll
        for (int k = 1; k < 6; k++) mma_rs64<O, 1, 1>(ct, h[4 * k], h[4 * k + 1], h[4 * k + 2], h[4 * k + 3], db + k * 128);
        wg_commit();
        wg_wait<1>();
      };
      auto rest = [&](auto off, int t) {
        constexpr int O = decltype(off)::value;
        const uint64_t db = d128(dN + (t & 3) * (TB >> 4));
        wg_fence();
#pragma unroll
        for (int k = 6; k < 14; k++) mma_rs64<O, 1, 1>(ct, h[4 * k], h[4 * k + 1], h[4 * k + 2], h[4 * k + 3], db + k * 128);
#pragma unroll
        for (int k = 0; k < 4; k++) mma_rs64<O, 1, 1>(ct, yf[4 * k], yf[4 * k + 1], yf[4 * k + 2], yf[4 * k + 3], db + (14 + k) * 128);
        wg_commit();
      };
      auto freeT = [&](int t) { if (elect) mbar_arrive(bars + 8 * (B_ET + t)); };
      const uint32_t peerZ = mapa(sb + OFF_Z + tid * 16, rank ^ 1), peerB = mapa(bars + 8 * B_Z, rank ^ 1);
      auto send_peer = [&](auto off, int z) {
        constexpr int O = decltype(off)::value;
        fence_regs<O, 32>(ct);
#pragma unroll
        for (int i = 0; i < 4; i++)
          asm volatile("st.async.weak.shared::cluster.mbarrier::complete_tx::bytes.v4.b32 [%0], {%1,%2,%3,%4}, [%5];" ::"r"(peerZ + z * U + i * 4096),
                       "r"(pack_bf16(ct[O + 8 * i], ct[O + 8 * i + 1])), "r"(pack_bf16(ct[O + 8 * i + 2], ct[O + 8 * i + 3])),
                       "r"(pack_bf16(ct[O + 8 * i + 4], ct[O + 8 * i + 5])), "r"(pack_bf16(ct[O + 8 * i + 6], ct[O + 8 * i + 7])), "r"(peerB + 8 * z) : "memory");
      };
      auto send_grid = [&](auto off, int z) {
        constexpr int O = decltype(off)::value;
        fence_regs<O, 32>(ct);
        mbar_wait(bars + 8 * (B_Z + z), 0);
        uint4* dst = g_part + (size_t)((rb * 8 + 2 * ((q4 + z + 1) & 3) + rank) * 3 + z) * 1024 + tid;
#pragma unroll
        for (int i = 0; i < 4; i++) {
          const uint4 p = *(const uint4*)(smem + OFF_Z + z * U + i * 4096 + tid * 16);
          st_x4(dst + i * 256, (pack_bf16(ct[O + 8 * i] + bf_lo(p.x), ct[O + 8 * i + 1] + bf_hi(p.x)) & ~1u) | tag,
                pack_bf16(ct[O + 8 * i + 2] + bf_lo(p.y), ct[O + 8 * i + 3] + bf_hi(p.y)),
                pack_bf16(ct[O + 8 * i + 4] + bf_lo(p.z), ct[O + 8 * i + 5] + bf_hi(p.z)),
                pack_bf16(ct[O + 8 * i + 6] + bf_lo(p.w), ct[O + 8 * i + 7] + bf_hi(p.w)));
        }
        __syncwarp();
        if (lane == 0) hint_add(&g_cntP[32 * (rb * 8 + 2 * ((q4 + z + 1) & 3) + rank) + z]);
      };
      asm volatile("barrier.cluster.wait.aligned;" ::: "memory");
      head(IC<0>(), 0);
      if (elect) asm volatile("mbarrier.arrive.shared::cluster.b64 _, [%0];" ::"r"(mapa(bars + 8 * B_RDY, rank ^ 1)) : "memory");
      fence_regs<0, 64>(ci);
#pragma unroll
      for (int i = 0; i < 16; i++) {
        const float gg = (i & 1) ? g1 : g0;
        yf[i] = pack_pin((ci[2 * i] + ci[33 + 2 * i]) * gg, (ci[2 * i + 1] - ci[32 + 2 * i]) * gg);
      }
      rest(IC<0>(), 0);
      if (tid == 0) PROF_EV(8);
      head(IC<32>(), 1); freeT(0); mbar_wait(bars + 8 * B_RDY, 0); send_peer(IC<0>(), 0); rest(IC<32>(), 1);
      head(IC<0>(), 2); freeT(1); send_peer(IC<32>(), 1); rest(IC<0>(), 2);
      head(IC<32>(), 3); freeT(2); send_peer(IC<0>(), 2); rest(IC<32>(), 3);
      head(IC<0>(), 4); freeT(3); send_grid(IC<32>(), 0); rest(IC<0>(), 4);
      head(IC<32>(), 5); send_grid(IC<0>(), 1); rest(IC<32>(), 5);
      head(IC<0>(), 6); send_grid(IC<32>(), 2); rest(IC<0>(), 6);
      head(IC<32>(), 7); send_peer(IC<0>(), 3);
      {
        const uint4* src = g_part + (size_t)(rb * 8 + j) * 3 * 1024 + tid;
        uint4 pv[12];
        mbar_wait(bars + 8 * (B_HP + 1), 0);
#pragma unroll
        for (int i = 0; i < 8; i++) pv[i] = ld_x4(src + i * 256);
        rest(IC<32>(), 7);
        if (tid == 0) PROF_EV(9);
        mbar_wait(bars + 8 * (B_HP + 2), 0);
        if (tid == 0) PROF_EV(24);
#pragma unroll
        for (int i = 8; i < 12; i++) pv[i] = ld_x4(src + i * 256);
        const uint32_t t0 = (uint32_t)clock();
        for (;;) {
          uint32_t bad = 0;
#pragma unroll
          for (int i = 0; i < 12; i++) bad |= pv[i].x ^ tag;
          if (!__any_sync(0xffffffffu, bad & 1)) break;
#pragma unroll
          for (int i = 0; i < 12; i++) pv[i] = ld_x4(src + i * 256);
          spin_guard(t0);
        }
        if (tid == 0) PROF_EV(14);
        float sum[32];
#pragma unroll
        for (int i = 0; i < 4; i++) {
          const uint32_t a[4] = {pv[i].x & ~1u, pv[i].y, pv[i].z, pv[i].w}, b[4] = {pv[4 + i].x & ~1u, pv[4 + i].y, pv[4 + i].z, pv[4 + i].w},
                         c[4] = {pv[8 + i].x & ~1u, pv[8 + i].y, pv[8 + i].z, pv[8 + i].w};
#pragma unroll
          for (int e = 0; e < 4; e++) {
            sum[8 * i + 2 * e] = bf_lo(a[e]) + bf_lo(b[e]) + bf_lo(c[e]);
            sum[8 * i + 2 * e + 1] = bf_hi(a[e]) + bf_hi(b[e]) + bf_hi(c[e]);
          }
        }
        mbar_wait(bars + 8 * (B_Z + 3), 0);
#pragma unroll
        for (int i = 0; i < 4; i++) {
          const uint4 p = *(const uint4*)(smem + OFF_Z + 3 * U + i * 4096 + tid * 16);
          const uint32_t a[4] = {p.x, p.y, p.z, p.w};
#pragma unroll
          for (int e = 0; e < 4; e++) { sum[8 * i + 2 * e] += bf_lo(a[e]); sum[8 * i + 2 * e + 1] += bf_hi(a[e]); }
        }
        wg_wait<0>();
        fence_regs<32, 32>(ct);
#pragma unroll
        for (int i = 0; i < 32; i++) sum[i] += ct[32 + i];
        const uint32_t stg = sb + OFF_T + warp * 2048;
        const int mr = (lane & 7) + ((lane >> 3) & 1) * 8, mc = lane >> 4;
#pragma unroll
        for (int i = 0; i < 4; i++) {
          const uint32_t a = stg + mr * 128 + (((2 * i + mc) ^ (mr & 7)) << 4);
          asm volatile("stmatrix.sync.aligned.m8n8.x4.shared.b16 [%0], {%1,%2,%3,%4};" ::"r"(a), "r"(pack_bf16(sum[8 * i], sum[8 * i + 1])),
                       "r"(pack_bf16(sum[8 * i + 2], sum[8 * i + 3])), "r"(pack_bf16(sum[8 * i + 4], sum[8 * i + 5])),
                       "r"(pack_bf16(sum[8 * i + 6], sum[8 * i + 7])) : "memory");
        }
        __syncwarp();
#pragma unroll
        for (int i = 0; i < 4; i++) {
          const int r = 4 * i + (lane >> 3), c = lane & 7;
          const uint4 v = *(const uint4*)(smem + OFF_T + warp * 2048 + r * 128 + ((c ^ (r & 7)) << 4));
          *(uint4*)(out + (size_t)(2 * rb + wg + 32 * (16 * w + r)) * 512 + 64 * j + 8 * c) = v;
        }
      }
      if (tid == 0) { g_epoch[blockIdx.x * 8] = ep + 1; PROF_EV(15); PROF_CK(41); }
    }
  }
}

typedef CUresult (*EncodeFn)(CUtensorMap*, CUtensorMapDataType, cuuint32_t, void*, const cuuint64_t*, const cuuint64_t*, const cuuint32_t*,
                             const cuuint32_t*, CUtensorMapInterleave, CUtensorMapSwizzle, CUtensorMapL2promotion, CUtensorMapFloatOOBfill);

static void encode(EncodeFn f, CUtensorMap* m, const void* base, int rank, const cuuint64_t* dims, const cuuint64_t* strides, const cuuint32_t* box,
                   CUtensorMapSwizzle sw) {
  cuuint32_t es[5] = {1, 1, 1, 1, 1};
  f(m, CU_TENSOR_MAP_DATA_TYPE_BFLOAT16, rank, (void*)base, dims, strides, box, es, CU_TENSOR_MAP_INTERLEAVE_NONE, sw,
    CU_TENSOR_MAP_L2_PROMOTION_L2_128B, CU_TENSOR_MAP_FLOAT_OOB_FILL_NONE);
}

extern "C" void kernel_launch(void* const* d_in, const int* in_sizes, int n_in, void* d_out, int out_size) {
  (void)in_sizes; (void)n_in; (void)out_size;
  const __nv_bfloat16* x = (const __nv_bfloat16*)d_in[0];
  const __nv_bfloat16* w_r = (const __nv_bfloat16*)d_in[1];
  const __nv_bfloat16* w_i = (const __nv_bfloat16*)d_in[2];
  const __nv_bfloat16* Wg = (const __nv_bfloat16*)d_in[4];
  const __nv_bfloat16* Wu = (const __nv_bfloat16*)d_in[5];
  const __nv_bfloat16* Wd = (const __nv_bfloat16*)d_in[6];
  const __nv_bfloat16* gw = (const __nv_bfloat16*)d_in[7];

  void* fp = nullptr; cudaDriverEntryPointQueryResult qr;
  cudaGetDriverEntryPoint("cuTensorMapEncodeTiled", &fp, cudaEnableDefault, &qr);
  EncodeFn enc = (EncodeFn)fp;
  void *pFT, *pET;
  cudaGetSymbolAddress(&pFT, g_FT); cudaGetSymbolAddress(&pET, g_ET);

  Maps mp;
  const CUtensorMapSwizzle S128 = CU_TENSOR_MAP_SWIZZLE_128B, S64 = CU_TENSOR_MAP_SWIZZLE_64B;
  { cuuint64_t d[3] = {512, 64, 32}, s[2] = {32768, 1024}; cuuint32_t b[3] = {64, 64, 2}; encode(enc, &mp.x, x, 3, d, s, b, S128); }
  { cuuint64_t d[2] = {512, 512}, s[1] = {1024}; cuuint32_t b[2] = {64, 64}; encode(enc, &mp.ft, pFT, 2, d, s, b, S128); }
  { cuuint64_t d[4] = {512, 2, 8, 32}, s[3] = {8192, 1024, 16384}; cuuint32_t b[4] = {64, 2, 8, 4}; encode(enc, &mp.fg, pFT, 4, d, s, b, S128); }
  { cuuint64_t d[4] = {64, 64, 2, 32}, s[3] = {8192, 128, 256}; cuuint32_t b[4] = {64, 64, 2, 1}; encode(enc, &mp.e, pET, 4, d, s, b, S128); }
  { cuuint64_t d[2] = {1792, 512}, s[1] = {3584}; cuuint32_t b[2] = {64, 64}, b2[2] = {32, 64};
    encode(enc, &mp.g64, Wg, 2, d, s, b, S128); encode(enc, &mp.u64, Wu, 2, d, s, b, S128);
    encode(enc, &mp.g32, Wg, 2, d, s, b2, S64); encode(enc, &mp.u32, Wu, 2, d, s, b2, S64); }
  { cuuint64_t d[2] = {512, 1792}, s[1] = {1024}; cuuint32_t b[2] = {64, 192}, b2[2] = {64, 32};
    encode(enc, &mp.d192, Wd, 2, d, s, b, S128); encode(enc, &mp.d32, Wd, 2, d, s, b2, S128); }

  { cuuint64_t d[4] = {264, 8, 8, 32}, s[3] = {512, 4112, 32896}; cuuint32_t b[4] = {24, 8, 1, 32};
    encode(enc, &mp.wr, w_r, 4, d, s, b, CU_TENSOR_MAP_SWIZZLE_NONE); encode(enc, &mp.wi, w_i, 4, d, s, b, CU_TENSOR_MAP_SWIZZLE_NONE); }

  cudaFuncSetAttribute(fused_kernel, cudaFuncAttributeMaxDynamicSharedMemorySize, SMEM_BYTES);
  fused_kernel<<<NCTA, 512, SMEM_BYTES>>>(mp, x, w_r, w_i, gw, Wd, (__nv_bfloat16*)d_out);
}
```

```cpp
#include <cuda_runtime.h>
#include <cuda_bf16.h>
#include <cuda.h>
#include <stdint.h>

namespace tbl {
constexpr double PI = 3.14159265358979323846264338327950288;
constexpr double sin_s(double x) { double t = x, s = x; for (int n = 1; n < 12; n++) { t *= -x * x / ((2 * n) * (2 * n + 1)); s += t; } return s; }
constexpr double cos_s(double x) { double t = 1, s = 1; for (int n = 1; n < 12; n++) { t *= -x * x / ((2 * n - 1) * (2 * n)); s += t; } return s; }
constexpr double cos2048(int m) {
  m &= 2047; if (m > 1024) m = 2048 - m;
  bool neg = false; if (m > 512) { m = 1024 - m; neg = true; }
  double v = (m <= 256) ? cos_s(2 * PI * m / 2048) : sin_s(2 * PI * (512 - m) / 2048);
  return neg ? -v : v;
}
constexpr uint16_t to_bf16(double v) {
  if (v == 0) return 0;
  uint16_t s = 0; if (v < 0) { s = 0x8000; v = -v; }
  int e = 0; while (v >= 2) { v /= 2; e++; } while (v < 1) { v *= 2; e--; }
  double m = (v - 1) * 128; int mi = (int)m; double fr = m - mi;
  if (fr > 0.5 || (fr == 0.5 && (mi & 1))) mi++;
  if (mi == 128) { mi = 0; e++; }
  return (uint16_t)(s | ((e + 127) << 7) | mi);
}
struct CosT { uint16_t v[2048]; constexpr CosT() : v() { for (int i = 0; i < 2048; i++) v[i] = to_bf16(cos2048(i)); } };
struct alignas(1024) FT {
  uint16_t v[512 * 512];
  constexpr FT() : v() {
    CosT c;
    for (int r = 0; r < 512; r++) {
      int k = (r >> 4) * 8 + (r & 7), e = (r >> 3) & 1;
      int mul = 4 * k, add = e ? 512 : 0;
      if (k == 0 && e == 1) { mul = 1024; add = 0; }
      for (int d = 0; d < 512; d++) v[r * 512 + d] = c.v[(d * mul + add) & 2047];
    }
  }
};
struct alignas(1024) ET {
  uint16_t v[2048 * 128];
  constexpr ET() : v() {
    CosT c;
    for (int s = 0; s < 2048; s++)
      for (int j = 0; j < 64; j++) { v[s * 128 + j] = c.v[(s * j) & 2047]; v[s * 128 + 64 + j] = c.v[(s * j + 512) & 2047]; }
  }
};
template <int A> struct W32 {
  static constexpr float c = (float)cos2048(A * 64);
  static constexpr float s = (float)cos2048(A * 64 - 512);
};
}

__device__ constexpr tbl::FT g_FT = tbl::FT();
__device__ constexpr tbl::ET g_ET = tbl::ET();

__device__ __align__(1024) uint2 g_X1p[128 * 32 * 64];
__device__ __align__(1024) float2 g_X1s[2 * 32 * 64];
__device__ __align__(1024) uint2 g_T[8 * 16 * 2 * 64 * 16];
__device__ __align__(1024) uint4 g_part[128 * 3 * 1024];
__device__ __align__(16) float g_gate[16 * 128];
__device__ __align__(16) float2 g_Wh[2 * 2048];
__device__ unsigned g_epoch[132 * 8];
__device__ unsigned g_cntX[8 * 32], g_cntT[8 * 32], g_cntP[128 * 32], g_cntW[32];
#define PROF_EV(i) do {} while (0)
#define PROF_CK(i) do {} while (0)

__device__ __forceinline__ uint32_t smem_u32(const void* p) { return (uint32_t)__cvta_generic_to_shared(p); }
__device__ __forceinline__ void mbar_init(uint32_t bar, uint32_t cnt) { asm volatile("mbarrier.init.shared::cta.b64 [%0], %1;" ::"r"(bar), "r"(cnt)); }
__device__ __forceinline__ void mbar_expect_tx(uint32_t bar, uint32_t bytes) { asm volatile("mbarrier.arrive.expect_tx.shared::cta.b64 _, [%0], %1;" ::"r"(bar), "r"(bytes) : "memory"); }
__device__ __forceinline__ void mbar_arrive(uint32_t bar) { asm volatile("mbarrier.arrive.shared::cta.b64 _, [%0];" ::"r"(bar) : "memory"); }
__device__ __forceinline__ bool mbar_try(uint32_t bar, uint32_t parity) {
  uint32_t ok;
  asm volatile("{\n.reg .pred p;\nmbarrier.try_wait.parity.shared::cta.b64 p, [%1], %2;\nselp.u32 %0, 1, 0, p;\n}" : "=r"(ok) : "r"(bar), "r"(parity) : "memory");
  return ok;
}
__device__ __forceinline__ void mbar_wait(uint32_t bar, uint32_t parity) {
  if (mbar_try(bar, parity)) return;
  const uint32_t t0 = (uint32_t)clock();
  while (!mbar_try(bar, parity)) { if ((uint32_t)clock() - t0 > (1u << 30)) __trap(); }
}
__device__ __forceinline__ void spin_guard(uint32_t t0) { if ((uint32_t)clock() - t0 > (1u << 30)) __trap(); }
__device__ __forceinline__ float tagf(float v, uint32_t tag) { return __uint_as_float((__float_as_uint(v) & ~1u) | tag); }
__device__ __forceinline__ float untag(float v) { return __uint_as_float(__float_as_uint(v) & ~1u); }
__device__ __forceinline__ void st_x2(float2* p, float a, float b) { asm volatile("st.relaxed.gpu.global.v2.f32 [%0], {%1,%2};" ::"l"(p), "f"(a), "f"(b) : "memory"); }
__device__ __forceinline__ float2 ld_x2(const float2* p) { float2 v; asm volatile("ld.relaxed.gpu.global.v2.f32 {%0,%1}, [%2];" : "=f"(v.x), "=f"(v.y) : "l"(p) : "memory"); return v; }
__device__ __forceinline__ void st_u2(uint2* p, uint32_t a, uint32_t b) { asm volatile("st.relaxed.gpu.global.v2.u32 [%0], {%1,%2};" ::"l"(p), "r"(a), "r"(b) : "memory"); }
__device__ __forceinline__ void prefetch2d(const CUtensorMap* m, int c0, int c1) { asm volatile("cp.async.bulk.prefetch.tensor.2d.L2.global [%0, {%1, %2}];" ::"l"(m), "r"(c0), "r"(c1) : "memory"); }
__device__ __forceinline__ void prefetch1d(const void* p, uint32_t bytes) { asm volatile("cp.async.bulk.prefetch.L2.global [%0], %1;" ::"l"(p), "r"(bytes) : "memory"); }
__device__ __forceinline__ uint32_t ld_x1(const void* p) { uint32_t v; asm volatile("ld.relaxed.gpu.global.u32 %0, [%1];" : "=r"(v) : "l"(p) : "memory"); return v; }
__device__ __forceinline__ uint4 ld_x4(const void* p) { uint4 v; asm volatile("ld.relaxed.gpu.global.v4.u32 {%0,%1,%2,%3}, [%4];" : "=r"(v.x), "=r"(v.y), "=r"(v.z), "=r"(v.w) : "l"(p) : "memory"); return v; }
__device__ __forceinline__ void st_x4(void* p, uint32_t a, uint32_t b, uint32_t c, uint32_t d) { asm volatile("st.relaxed.gpu.global.v4.u32 [%0], {%1,%2,%3,%4};" ::"l"(p), "r"(a), "r"(b), "r"(c), "r"(d) : "memory"); }
__device__ __forceinline__ uint32_t mapa(uint32_t a, uint32_t cta) { uint32_t r; asm volatile("mapa.shared::cluster.u32 %0, %1, %2;" : "=r"(r) : "r"(a), "r"(cta)); return r; }
__device__ __forceinline__ void hint_add(unsigned* p) { asm volatile("red.relaxed.gpu.global.add.u32 [%0], 1;" ::"l"(p) : "memory"); }
__device__ __forceinline__ void hint_wait(const unsigned* p, unsigned target) {
  const uint32_t t0 = (uint32_t)clock();
  while ((int)(ld_x1(p) - target) < 0) spin_guard(t0);
}
__device__ __forceinline__ void load32_tagged(float2 (&v)[32], const float2* src, int stride, uint32_t tag) {
  const uint32_t t0 = (uint32_t)clock();
  for (;;) {
    uint32_t bad = 0;
#pragma unroll
    for (int a = 0; a < 32; a++) v[a] = ld_x2(src + a * stride);
#pragma unroll
    for (int a = 0; a < 32; a++) bad |= __float_as_uint(v[a].x) ^ tag;
    if (!__any_sync(0xffffffffu, bad & 1)) break;
    spin_guard(t0);
  }
#pragma unroll
  for (int a = 0; a < 32; a++) v[a].x = untag(v[a].x);
}
__device__ __forceinline__ void tma2d(uint32_t dst, const CUtensorMap* m, uint32_t bar, int c0, int c1) {
  asm volatile("cp.async.bulk.tensor.2d.shared::cluster.global.mbarrier::complete_tx::bytes [%0], [%1, {%3, %4}], [%2];" ::"r"(dst), "l"(m), "r"(bar), "r"(c0), "r"(c1) : "memory");
}
__device__ __forceinline__ void tma3d(uint32_t dst, const CUtensorMap* m, uint32_t bar, int c0, int c1, int c2) {
  asm volatile("cp.async.bulk.tensor.3d.shared::cluster.global.mbarrier::complete_tx::bytes [%0], [%1, {%3, %4, %5}], [%2];" ::"r"(dst), "l"(m), "r"(bar), "r"(c0), "r"(c1), "r"(c2) : "memory");
}
__device__ __forceinline__ void tma4d(uint32_t dst, const CUtensorMap* m, uint32_t bar, int c0, int c1, int c2, int c3) {
  asm volatile("cp.async.bulk.tensor.4d.shared::cluster.global.mbarrier::complete_tx::bytes [%0], [%1, {%3, %4, %5, %6}], [%2];" ::"r"(dst), "l"(m), "r"(bar), "r"(c0), "r"(c1), "r"(c2), "r"(c3) : "memory");
}
__device__ __forceinline__ void wg_fence() { asm volatile("wgmma.fence.sync.aligned;" ::: "memory"); }
__device__ __forceinline__ void wg_commit() { asm volatile("wgmma.commit_group.sync.aligned;" ::: "memory"); }
template <int N> __device__ __forceinline__ void wg_wait() { asm volatile("wgmma.wait_group.sync.aligned %0;" ::"n"(N) : "memory"); }
template <int O, int N, int NN> __device__ __forceinline__ void fence_regs(float (&d)[NN]) {
#pragma unroll
  for (int i = 0; i < N; i++) asm volatile("" : "+f"(d[O + i])::"memory");
}
__device__ __forceinline__ uint32_t pack_bf16(float lo, float hi) {
  uint32_t r; asm("cvt.rn.bf16x2.f32 %0, %1, %2;" : "=r"(r) : "f"(hi), "f"(lo)); return r;
}
__device__ __forceinline__ uint32_t pack_pin(float lo, float hi) {
  uint32_t r; asm volatile("cvt.rn.bf16x2.f32 %0, %1, %2;" : "=r"(r) : "f"(hi), "f"(lo) : "memory"); return r;
}
__device__ __forceinline__ float bf_lo(uint32_t u) { return __uint_as_float(u << 16); }
__device__ __forceinline__ float bf_hi(uint32_t u) { return __uint_as_float(u & 0xffff0000u); }

__device__ __forceinline__ uint64_t d128(uint32_t lo) { uint64_t d; asm("mov.b64 %0, {%1, 0x40000040};" : "=l"(d) : "r"(lo)); return d; }
__device__ __forceinline__ uint64_t d64(uint32_t lo) { uint64_t d; asm("mov.b64 %0, {%1, 0x80000020};" : "=l"(d) : "r"(lo)); return d; }
template<int O,int TB,int ACC,int NN> __device__ __forceinline__ void mma_ss64(float (&d)[NN], uint64_t da, uint64_t db, int sd = 0){
  if constexpr (ACC == 1) asm volatile("wgmma.mma_async.sync.aligned.m64n64k16.f32.bf16.bf16 {%0,%1,%2,%3,%4,%5,%6,%7,%8,%9,%10,%11,%12,%13,%14,%15,%16,%17,%18,%19,%20,%21,%22,%23,%24,%25,%26,%27,%28,%29,%30,%31}, %32, %33, 1, 1, 1, 0, %34;"
   : "+f"(d[O+0]), "+f"(d[O+1]), "+f"(d[O+2]), "+f"(d[O+3]), "+f"(d[O+4]), "+f"(d[O+5]), "+f"(d[O+6]), "+f"(d[O+7]), "+f"(d[O+8]), "+f"(d[O+9]), "+f"(d[O+10]), "+f"(d[O+11]), "+f"(d[O+12]), "+f"(d[O+13]), "+f"(d[O+14]), "+f"(d[O+15]), "+f"(d[O+16]), "+f"(d[O+17]), "+f"(d[O+18]), "+f"(d[O+19]), "+f"(d[O+20]), "+f"(d[O+21]), "+f"(d[O+22]), "+f"(d[O+23]), "+f"(d[O+24]), "+f"(d[O+25]), "+f"(d[O+26]), "+f"(d[O+27]), "+f"(d[O+28]), "+f"(d[O+29]), "+f"(d[O+30]), "+f"(d[O+31])
   : "l"(da), "l"(db), "n"(TB));
  else if constexpr (ACC == 0) asm volatile("wgmma.mma_async.sync.aligned.m64n64k16.f32.bf16.bf16 {%0,%1,%2,%3,%4,%5,%6,%7,%8,%9,%10,%11,%12,%13,%14,%15,%16,%17,%18,%19,%20,%21,%22,%23,%24,%25,%26,%27,%28,%29,%30,%31}, %32, %33, 0, 1, 1, 0, %34;"
   : "=f"(d[O+0]), "=f"(d[O+1]), "=f"(d[O+2]), "=f"(d[O+3]), "=f"(d[O+4]), "=f"(d[O+5]), "=f"(d[O+6]), "=f"(d[O+7]), "=f"(d[O+8]), "=f"(d[O+9]), "=f"(d[O+10]), "=f"(d[O+11]), "=f"(d[O+12]), "=f"(d[O+13]), "=f"(d[O+14]), "=f"(d[O+15]), "=f"(d[O+16]), "=f"(d[O+17]), "=f"(d[O+18]), "=f"(d[O+19]), "=f"(d[O+20]), "=f"(d[O+21]), "=f"(d[O+22]), "=f"(d[O+23]), "=f"(d[O+24]), "=f"(d[O+25]), "=f"(d[O+26]), "=f"(d[O+27]), "=f"(d[O+28]), "=f"(d[O+29]), "=f"(d[O+30]), "=f"(d[O+31])
   : "l"(da), "l"(db), "n"(TB));
  else asm volatile("{\n.reg .pred p;\nsetp.ne.b32 p, %35, 0;\nwgmma.mma_async.sync.aligned.m64n64k16.f32.bf16.bf16 {%0,%1,%2,%3,%4,%5,%6,%7,%8,%9,%10,%11,%12,%13,%14,%15,%16,%17,%18,%19,%20,%21,%22,%23,%24,%25,%26,%27,%28,%29,%30,%31}, %32, %33, p, 1, 1, 0, %34;\n}"
   : "+f"(d[O+0]), "+f"(d[O+1]), "+f"(d[O+2]), "+f"(d[O+3]), "+f"(d[O+4]), "+f"(d[O+5]), "+f"(d[O+6]), "+f"(d[O+7]), "+f"(d[O+8]), "+f"(d[O+9]), "+f"(d[O+10]), "+f"(d[O+11]), "+f"(d[O+12]), "+f"(d[O+13]), "+f"(d[O+14]), "+f"(d[O+15]), "+f"(d[O+16]), "+f"(d[O+17]), "+f"(d[O+18]), "+f"(d[O+19]), "+f"(d[O+20]), "+f"(d[O+21]), "+f"(d[O+22]), "+f"(d[O+23]), "+f"(d[O+24]), "+f"(d[O+25]), "+f"(d[O+26]), "+f"(d[O+27]), "+f"(d[O+28]), "+f"(d[O+29]), "+f"(d[O+30]), "+f"(d[O+31])
   : "l"(da), "l"(db), "n"(TB), "r"(sd));
}
template<int O,int TB,int ACC,int NN> __device__ __forceinline__ void mma_rs64(float (&d)[NN], uint32_t a0, uint32_t a1, uint32_t a2, uint32_t a3, uint64_t db, int sd = 0){
  if constexpr (ACC == 1) asm volatile("wgmma.mma_async.sync.aligned.m64n64k16.f32.bf16.bf16 {%0,%1,%2,%3,%4,%5,%6,%7,%8,%9,%10,%11,%12,%13,%14,%15,%16,%17,%18,%19,%20,%21,%22,%23,%24,%25,%26,%27,%28,%29,%30,%31}, {%32,%33,%34,%35}, %36, 1, 1, 1, %37;"
   : "+f"(d[O+0]), "+f"(d[O+1]), "+f"(d[O+2]), "+f"(d[O+3]), "+f"(d[O+4]), "+f"(d[O+5]), "+f"(d[O+6]), "+f"(d[O+7]), "+f"(d[O+8]), "+f"(d[O+9]), "+f"(d[O+10]), "+f"(d[O+11]), "+f"(d[O+12]), "+f"(d[O+13]), "+f"(d[O+14]), "+f"(d[O+15]), "+f"(d[O+16]), "+f"(d[O+17]), "+f"(d[O+18]), "+f"(d[O+19]), "+f"(d[O+20]), "+f"(d[O+21]), "+f"(d[O+22]), "+f"(d[O+23]), "+f"(d[O+24]), "+f"(d[O+25]), "+f"(d[O+26]), "+f"(d[O+27]), "+f"(d[O+28]), "+f"(d[O+29]), "+f"(d[O+30]), "+f"(d[O+31])
   : "r"(a0), "r"(a1), "r"(a2), "r"(a3), "l"(db), "n"(TB));
  else if constexpr (ACC == 0) asm volatile("wgmma.mma_async.sync.aligned.m64n64k16.f32.bf16.bf16 {%0,%1,%2,%3,%4,%5,%6,%7,%8,%9,%10,%11,%12,%13,%14,%15,%16,%17,%18,%19,%20,%21,%22,%23,%24,%25,%26,%27,%28,%29,%30,%31}, {%32,%33,%34,%35}, %36, 0, 1, 1, %37;"
   : "=f"(d[O+0]), "=f"(d[O+1]), "=f"(d[O+2]), "=f"(d[O+3]), "=f"(d[O+4]), "=f"(d[O+5]), "=f"(d[O+6]), "=f"(d[O+7]), "=f"(d[O+8]), "=f"(d[O+9]), "=f"(d[O+10]), "=f"(d[O+11]), "=f"(d[O+12]), "=f"(d[O+13]), "=f"(d[O+14]), "=f"(d[O+15]), "=f"(d[O+16]), "=f"(d[O+17]), "=f"(d[O+18]), "=f"(d[O+19]), "=f"(d[O+20]), "=f"(d[O+21]), "=f"(d[O+22]), "=f"(d[O+23]), "=f"(d[O+24]), "=f"(d[O+25]), "=f"(d[O+26]), "=f"(d[O+27]), "=f"(d[O+28]), "=f"(d[O+29]), "=f"(d[O+30]), "=f"(d[O+31])
   : "r"(a0), "r"(a1), "r"(a2), "r"(a3), "l"(db), "n"(TB));
  else asm volatile("{\n.reg .pred p;\nsetp.ne.b32 p, %38, 0;\nwgmma.mma_async.sync.aligned.m64n64k16.f32.bf16.bf16 {%0,%1,%2,%3,%4,%5,%6,%7,%8,%9,%10,%11,%12,%13,%14,%15,%16,%17,%18,%19,%20,%21,%22,%23,%24,%25,%26,%27,%28,%29,%30,%31}, {%32,%33,%34,%35}, %36, p, 1, 1, %37;\n}"
   : "+f"(d[O+0]), "+f"(d[O+1]), "+f"(d[O+2]), "+f"(d[O+3]), "+f"(d[O+4]), "+f"(d[O+5]), "+f"(d[O+6]), "+f"(d[O+7]), "+f"(d[O+8]), "+f"(d[O+9]), "+f"(d[O+10]), "+f"(d[O+11]), "+f"(d[O+12]), "+f"(d[O+13]), "+f"(d[O+14]), "+f"(d[O+15]), "+f"(d[O+16]), "+f"(d[O+17]), "+f"(d[O+18]), "+f"(d[O+19]), "+f"(d[O+20]), "+f"(d[O+21]), "+f"(d[O+22]), "+f"(d[O+23]), "+f"(d[O+24]), "+f"(d[O+25]), "+f"(d[O+26]), "+f"(d[O+27]), "+f"(d[O+28]), "+f"(d[O+29]), "+f"(d[O+30]), "+f"(d[O+31])
   : "r"(a0), "r"(a1), "r"(a2), "r"(a3), "l"(db), "n"(TB), "r"(sd));
}
template<int O,int TB,int ACC,int NN> __device__ __forceinline__ void mma_ss128(float (&d)[NN], uint64_t da, uint64_t db, int sd = 0){
  if constexpr (ACC == 1) asm volatile("wgmma.mma_async.sync.aligned.m64n128k16.f32.bf16.bf16 {%0,%1,%2,%3,%4,%5,%6,%7,%8,%9,%10,%11,%12,%13,%14,%15,%16,%17,%18,%19,%20,%21,%22,%23,%24,%25,%26,%27,%28,%29,%30,%31,%32,%33,%34,%35,%36,%37,%38,%39,%40,%41,%42,%43,%44,%45,%46,%47,%48,%49,%50,%51,%52,%53,%54,%55,%56,%57,%58,%59,%60,%61,%62,%63}, %64, %65, 1, 1, 1, 0, %66;"
   : "+f"(d[O+0]), "+f"(d[O+1]), "+f"(d[O+2]), "+f"(d[O+3]), "+f"(d[O+4]), "+f"(d[O+5]), "+f"(d[O+6]), "+f"(d[O+7]), "+f"(d[O+8]), "+f"(d[O+9]), "+f"(d[O+10]), "+f"(d[O+11]), "+f"(d[O+12]), "+f"(d[O+13]), "+f"(d[O+14]), "+f"(d[O+15]), "+f"(d[O+16]), "+f"(d[O+17]), "+f"(d[O+18]), "+f"(d[O+19]), "+f"(d[O+20]), "+f"(d[O+21]), "+f"(d[O+22]), "+f"(d[O+23]), "+f"(d[O+24]), "+f"(d[O+25]), "+f"(d[O+26]), "+f"(d[O+27]), "+f"(d[O+28]), "+f"(d[O+29]), "+f"(d[O+30]), "+f"(d[O+31]), "+f"(d[O+32]), "+f"(d[O+33]), "+f"(d[O+34]), "+f"(d[O+35]), "+f"(d[O+36]), "+f"(d[O+37]), "+f"(d[O+38]), "+f"(d[O+39]), "+f"(d[O+40]), "+f"(d[O+41]), "+f"(d[O+42]), "+f"(d[O+43]), "+f"(d[O+44]), "+f"(d[O+45]), "+f"(d[O+46]), "+f"(d[O+47]), "+f"(d[O+48]), "+f"(d[O+49]), "+f"(d[O+50]), "+f"(d[O+51]), "+f"(d[O+52]), "+f"(d[O+53]), "+f"(d[O+54]), "+f"(d[O+55]), "+f"(d[O+56]), "+f"(d[O+57]), "+f"(d[O+58]), "+f"(d[O+59]), "+f"(d[O+60]), "+f"(d[O+61]), "+f"(d[O+62]), "+f"(d[O+63])
   : "l"(da), "l"(db), "n"(TB));
  else if constexpr (ACC == 0) asm volatile("wgmma.mma_async.sync.aligned.m64n128k16.f32.bf16.bf16 {%0,%1,%2,%3,%4,%5,%6,%7,%8,%9,%10,%11,%12,%13,%14,%15,%16,%17,%18,%19,%20,%21,%22,%23,%24,%25,%26,%27,%28,%29,%30,%31,%32,%33,%34,%35,%36,%37,%38,%39,%40,%41,%42,%43,%44,%45,%46,%47,%48,%49,%50,%51,%52,%53,%54,%55,%56,%57,%58,%59,%60,%61,%62,%63}, %64, %65, 0, 1, 1, 0, %66;"
   : "=f"(d[O+0]), "=f"(d[O+1]), "=f"(d[O+2]), "=f"(d[O+3]), "=f"(d[O+4]), "=f"(d[O+5]), "=f"(d[O+6]), "=f"(d[O+7]), "=f"(d[O+8]), "=f"(d[O+9]), "=f"(d[O+10]), "=f"(d[O+11]), "=f"(d[O+12]), "=f"(d[O+13]), "=f"(d[O+14]), "=f"(d[O+15]), "=f"(d[O+16]), "=f"(d[O+17]), "=f"(d[O+18]), "=f"(d[O+19]), "=f"(d[O+20]), "=f"(d[O+21]), "=f"(d[O+22]), "=f"(d[O+23]), "=f"(d[O+24]), "=f"(d[O+25]), "=f"(d[O+26]), "=f"(d[O+27]), "=f"(d[O+28]), "=f"(d[O+29]), "=f"(d[O+30]), "=f"(d[O+31]), "=f"(d[O+32]), "=f"(d[O+33]), "=f"(d[O+34]), "=f"(d[O+35]), "=f"(d[O+36]), "=f"(d[O+37]), "=f"(d[O+38]), "=f"(d[O+39]), "=f"(d[O+40]), "=f"(d[O+41]), "=f"(d[O+42]), "=f"(d[O+43]), "=f"(d[O+44]), "=f"(d[O+45]), "=f"(d[O+46]), "=f"(d[O+47]), "=f"(d[O+48]), "=f"(d[O+49]), "=f"(d[O+50]), "=f"(d[O+51]), "=f"(d[O+52]), "=f"(d[O+53]), "=f"(d[O+54]), "=f"(d[O+55]), "=f"(d[O+56]), "=f"(d[O+57]), "=f"(d[O+58]), "=f"(d[O+59]), "=f"(d[O+60]), "=f"(d[O+61]), "=f"(d[O+62]), "=f"(d[O+63])
   : "l"(da), "l"(db), "n"(TB));
  else asm volatile("{\n.reg .pred p;\nsetp.ne.b32 p, %67, 0;\nwgmma.mma_async.sync.aligned.m64n128k16.f32.bf16.bf16 {%0,%1,%2,%3,%4,%5,%6,%7,%8,%9,%10,%11,%12,%13,%14,%15,%16,%17,%18,%19,%20,%21,%22,%23,%24,%25,%26,%27,%28,%29,%30,%31,%32,%33,%34,%35,%36,%37,%38,%39,%40,%41,%42,%43,%44,%45,%46,%47,%48,%49,%50,%51,%52,%53,%54,%55,%56,%57,%58,%59,%60,%61,%62,%63}, %64, %65, p, 1, 1, 0, %66;\n}"
   : "+f"(d[O+0]), "+f"(d[O+1]), "+f"(d[O+2]), "+f"(d[O+3]), "+f"(d[O+4]), "+f"(d[O+5]), "+f"(d[O+6]), "+f"(d[O+7]), "+f"(d[O+8]), "+f"(d[O+9]), "+f"(d[O+10]), "+f"(d[O+11]), "+f"(d[O+12]), "+f"(d[O+13]), "+f"(d[O+14]), "+f"(d[O+15]), "+f"(d[O+16]), "+f"(d[O+17]), "+f"(d[O+18]), "+f"(d[O+19]), "+f"(d[O+20]), "+f"(d[O+21]), "+f"(d[O+22]), "+f"(d[O+23]), "+f"(d[O+24]), "+f"(d[O+25]), "+f"(d[O+26]), "+f"(d[O+27]), "+f"(d[O+28]), "+f"(d[O+29]), "+f"(d[O+30]), "+f"(d[O+31]), "+f"(d[O+32]), "+f"(d[O+33]), "+f"(d[O+34]), "+f"(d[O+35]), "+f"(d[O+36]), "+f"(d[O+37]), "+f"(d[O+38]), "+f"(d[O+39]), "+f"(d[O+40]), "+f"(d[O+41]), "+f"(d[O+42]), "+f"(d[O+43]), "+f"(d[O+44]), "+f"(d[O+45]), "+f"(d[O+46]), "+f"(d[O+47]), "+f"(d[O+48]), "+f"(d[O+49]), "+f"(d[O+50]), "+f"(d[O+51]), "+f"(d[O+52]), "+f"(d[O+53]), "+f"(d[O+54]), "+f"(d[O+55]), "+f"(d[O+56]), "+f"(d[O+57]), "+f"(d[O+58]), "+f"(d[O+59]), "+f"(d[O+60]), "+f"(d[O+61]), "+f"(d[O+62]), "+f"(d[O+63])
   : "l"(da), "l"(db), "n"(TB), "r"(sd));
}
template<int O,int TB,int ACC,int NN> __device__ __forceinline__ void mma_rs128(float (&d)[NN], uint32_t a0, uint32_t a1, uint32_t a2, uint32_t a3, uint64_t db, int sd = 0){
  if constexpr (ACC == 1) asm volatile("wgmma.mma_async.sync.aligned.m64n128k16.f32.bf16.bf16 {%0,%1,%2,%3,%4,%5,%6,%7,%8,%9,%10,%11,%12,%13,%14,%15,%16,%17,%18,%19,%20,%21,%22,%23,%24,%25,%26,%27,%28,%29,%30,%31,%32,%33,%34,%35,%36,%37,%38,%39,%40,%41,%42,%43,%44,%45,%46,%47,%48,%49,%50,%51,%52,%53,%54,%55,%56,%57,%58,%59,%60,%61,%62,%63}, {%64,%65,%66,%67}, %68, 1, 1, 1, %69;"
   : "+f"(d[O+0]), "+f"(d[O+1]), "+f"(d[O+2]), "+f"(d[O+3]), "+f"(d[O+4]), "+f"(d[O+5]), "+f"(d[O+6]), "+f"(d[O+7]), "+f"(d[O+8]), "+f"(d[O+9]), "+f"(d[O+10]), "+f"(d[O+11]), "+f"(d[O+12]), "+f"(d[O+13]), "+f"(d[O+14]), "+f"(d[O+15]), "+f"(d[O+16]), "+f"(d[O+17]), "+f"(d[O+18]), "+f"(d[O+19]), "+f"(d[O+20]), "+f"(d[O+21]), "+f"(d[O+22]), "+f"(d[O+23]), "+f"(d[O+24]), "+f"(d[O+25]), "+f"(d[O+26]), "+f"(d[O+27]), "+f"(d[O+28]), "+f"(d[O+29]), "+f"(d[O+30]), "+f"(d[O+31]), "+f"(d[O+32]), "+f"(d[O+33]), "+f"(d[O+34]), "+f"(d[O+35]), "+f"(d[O+36]), "+f"(d[O+37]), "+f"(d[O+38]), "+f"(d[O+39]), "+f"(d[O+40]), "+f"(d[O+41]), "+f"(d[O+42]), "+f"(d[O+43]), "+f"(d[O+44]), "+f"(d[O+45]), "+f"(d[O+46]), "+f"(d[O+47]), "+f"(d[O+48]), "+f"(d[O+49]), "+f"(d[O+50]), "+f"(d[O+51]), "+f"(d[O+52]), "+f"(d[O+53]), "+f"(d[O+54]), "+f"(d[O+55]), "+f"(d[O+56]), "+f"(d[O+57]), "+f"(d[O+58]), "+f"(d[O+59]), "+f"(d[O+60]), "+f"(d[O+61]), "+f"(d[O+62]), "+f"(d[O+63])
   : "r"(a0), "r"(a1), "r"(a2), "r"(a3), "l"(db), "n"(TB));
  else if constexpr (ACC == 0) asm volatile("wgmma.mma_async.sync.aligned.m64n128k16.f32.bf16.bf16 {%0,%1,%2,%3,%4,%5,%6,%7,%8,%9,%10,%11,%12,%13,%14,%15,%16,%17,%18,%19,%20,%21,%22,%23,%24,%25,%26,%27,%28,%29,%30,%31,%32,%33,%34,%35,%36,%37,%38,%39,%40,%41,%42,%43,%44,%45,%46,%47,%48,%49,%50,%51,%52,%53,%54,%55,%56,%57,%58,%59,%60,%61,%62,%63}, {%64,%65,%66,%67}, %68, 0, 1, 1, %69;"
   : "=f"(d[O+0]), "=f"(d[O+1]), "=f"(d[O+2]), "=f"(d[O+3]), "=f"(d[O+4]), "=f"(d[O+5]), "=f"(d[O+6]), "=f"(d[O+7]), "=f"(d[O+8]), "=f"(d[O+9]), "=f"(d[O+10]), "=f"(d[O+11]), "=f"(d[O+12]), "=f"(d[O+13]), "=f"(d[O+14]), "=f"(d[O+15]), "=f"(d[O+16]), "=f"(d[O+17]), "=f"(d[O+18]), "=f"(d[O+19]), "=f"(d[O+20]), "=f"(d[O+21]), "=f"(d[O+22]), "=f"(d[O+23]), "=f"(d[O+24]), "=f"(d[O+25]), "=f"(d[O+26]), "=f"(d[O+27]), "=f"(d[O+28]), "=f"(d[O+29]), "=f"(d[O+30]), "=f"(d[O+31]), "=f"(d[O+32]), "=f"(d[O+33]), "=f"(d[O+34]), "=f"(d[O+35]), "=f"(d[O+36]), "=f"(d[O+37]), "=f"(d[O+38]), "=f"(d[O+39]), "=f"(d[O+40]), "=f"(d[O+41]), "=f"(d[O+42]), "=f"(d[O+43]), "=f"(d[O+44]), "=f"(d[O+45]), "=f"(d[O+46]), "=f"(d[O+47]), "=f"(d[O+48]), "=f"(d[O+49]), "=f"(d[O+50]), "=f"(d[O+51]), "=f"(d[O+52]), "=f"(d[O+53]), "=f"(d[O+54]), "=f"(d[O+55]), "=f"(d[O+56]), "=f"(d[O+57]), "=f"(d[O+58]), "=f"(d[O+59]), "=f"(d[O+60]), "=f"(d[O+61]), "=f"(d[O+62]), "=f"(d[O+63])
   : "r"(a0), "r"(a1), "r"(a2), "r"(a3), "l"(db), "n"(TB));
  else asm volatile("{\n.reg .pred p;\nsetp.ne.b32 p, %70, 0;\nwgmma.mma_async.sync.aligned.m64n128k16.f32.bf16.bf16 {%0,%1,%2,%3,%4,%5,%6,%7,%8,%9,%10,%11,%12,%13,%14,%15,%16,%17,%18,%19,%20,%21,%22,%23,%24,%25,%26,%27,%28,%29,%30,%31,%32,%33,%34,%35,%36,%37,%38,%39,%40,%41,%42,%43,%44,%45,%46,%47,%48,%49,%50,%51,%52,%53,%54,%55,%56,%57,%58,%59,%60,%61,%62,%63}, {%64,%65,%66,%67}, %68, p, 1, 1, %69;\n}"
   : "+f"(d[O+0]), "+f"(d[O+1]), "+f"(d[O+2]), "+f"(d[O+3]), "+f"(d[O+4]), "+f"(d[O+5]), "+f"(d[O+6]), "+f"(d[O+7]), "+f"(d[O+8]), "+f"(d[O+9]), "+f"(d[O+10]), "+f"(d[O+11]), "+f"(d[O+12]), "+f"(d[O+13]), "+f"(d[O+14]), "+f"(d[O+15]), "+f"(d[O+16]), "+f"(d[O+17]), "+f"(d[O+18]), "+f"(d[O+19]), "+f"(d[O+20]), "+f"(d[O+21]), "+f"(d[O+22]), "+f"(d[O+23]), "+f"(d[O+24]), "+f"(d[O+25]), "+f"(d[O+26]), "+f"(d[O+27]), "+f"(d[O+28]), "+f"(d[O+29]), "+f"(d[O+30]), "+f"(d[O+31]), "+f"(d[O+32]), "+f"(d[O+33]), "+f"(d[O+34]), "+f"(d[O+35]), "+f"(d[O+36]), "+f"(d[O+37]), "+f"(d[O+38]), "+f"(d[O+39]), "+f"(d[O+40]), "+f"(d[O+41]), "+f"(d[O+42]), "+f"(d[O+43]), "+f"(d[O+44]), "+f"(d[O+45]), "+f"(d[O+46]), "+f"(d[O+47]), "+f"(d[O+48]), "+f"(d[O+49]), "+f"(d[O+50]), "+f"(d[O+51]), "+f"(d[O+52]), "+f"(d[O+53]), "+f"(d[O+54]), "+f"(d[O+55]), "+f"(d[O+56]), "+f"(d[O+57]), "+f"(d[O+58]), "+f"(d[O+59]), "+f"(d[O+60]), "+f"(d[O+61]), "+f"(d[O+62]), "+f"(d[O+63])
   : "r"(a0), "r"(a1), "r"(a2), "r"(a3), "l"(db), "n"(TB), "r"(sd));
}

__host__ __device__ constexpr int brev(int a, int bits) { int r = 0; for (int i = 0; i < bits; i++) r |= ((a >> i) & 1) << (bits - 1 - i); return r; }
__host__ __device__ constexpr int ilog2(int n) { return n <= 1 ? 0 : 1 + ilog2(n / 2); }
template <int SG, int A> __device__ __forceinline__ void bfly(float2& a, float2& b) {
  if constexpr (A == 0) {
    float tr = a.x - b.x, ti = a.y - b.y; a.x += b.x; a.y += b.y; b.x = tr; b.y = ti;
  } else if constexpr (A == 8) {
    float pr = SG > 0 ? -b.y : b.y, pi = SG > 0 ? b.x : -b.x;
    b.x = a.x - pr; b.y = a.y - pi; a.x += pr; a.y += pi;
  } else {
    constexpr float wr = tbl::W32<A>::c, wi = SG * tbl::W32<A>::s;
    float tr = fmaf(wr, b.x, a.x), ti = fmaf(wr, b.y, a.y);
    tr = fmaf(-wi, b.y, tr); ti = fmaf(wi, b.x, ti);
    b.x = fmaf(2.f, a.x, -tr); b.y = fmaf(2.f, a.y, -ti); a.x = tr; a.y = ti;
  }
}
template <int SG, int N, int O, int ST, int A> __device__ __forceinline__ void dft_comb(float2 (&x)[32]) {
  if constexpr (A < N / 2) {
    constexpr int p = O + 2 * ST * brev(A, ilog2(N / 2));
    bfly<SG, A * (32 / N)>(x[p], x[p + ST]);
    dft_comb<SG, N, O, ST, A + 1>(x);
  }
}
template <int SG, int N, int O, int ST> __device__ __forceinline__ void dft(float2 (&x)[32]) {
  if constexpr (N > 1) {
    dft<SG, N / 2, O, 2 * ST>(x);
    dft<SG, N / 2, O + ST, 2 * ST>(x);
    dft_comb<SG, N, O, ST, 0>(x);
  }
}

#define TPACE 40
#define PFMODE 0
#define MAPMODE 0
template <int V> struct IC { static constexpr int value = V; };
struct Maps { CUtensorMap x, ft, g32, u32, g64, u64, e, wr, wi, d192, d32, fg; };

constexpr int NCTA = 132;
constexpr int U = 16384;
constexpr int TB = 36864;
constexpr int OFF_RING = 8 * U, OFF_Z = 9 * U, OFF_WRAW = 12 * U, OFF_T = 13 * U;
constexpr int OFF_BAR = 14 * U;
constexpr int SMEM_BYTES = OFF_BAR + 512;
constexpr int B_FX = 0, B_FA = 8, B_FT = 12, B_Z = 16, B_W = 20, B_HX = 21, B_HT = 22, B_HP = 23;
constexpr int B_EA = 26, B_ET = 30, B_RDY = 34;
constexpr int B_T = 35, NBAR = 36;

__global__ void __cluster_dims__(2, 1, 1) __launch_bounds__(512, 1)
fused_kernel(const __grid_constant__ Maps maps, const __nv_bfloat16* __restrict__ x, const __nv_bfloat16* __restrict__ w_r,
             const __nv_bfloat16* __restrict__ w_i, const __nv_bfloat16* __restrict__ gate_w, const __nv_bfloat16* __restrict__ Wd,
             __nv_bfloat16* __restrict__ out) {
  extern __shared__ __align__(1024) uint8_t smem[];
  const uint32_t sb = smem_u32(smem);
  const uint32_t bars = sb + OFF_BAR;
  const int tid = threadIdx.x, lane = tid & 31;
  const int warp = __shfl_sync(0xffffffffu, tid >> 5, 0);
  const bool helper = blockIdx.x >= 128;
  const int cl = (blockIdx.x >> 1) & 63, rank = blockIdx.x & 1;
  const int q4 = cl & 3, rb = cl >> 2;
  const int j = 2 * q4 + rank;
  const int f_full = 448 * q4 + (rank ? 256 : 0);
  const int f_half = 448 * q4 + (rank ? 224 : 192);
  const int kg = 2 * j + (rb >> 3), tn = rb & 7;

  if (tid == 64) { PROF_EV(0); PROF_CK(40); }
  auto ring_load = [&](int n) {
    const uint32_t fb = bars + 8 * (B_FA + (n & 3)), dst = sb + OFF_RING + (n & 3) * U;
    mbar_expect_tx(fb, U);
    if (n < 8) {
      tma2d(dst, &maps.ft, fb, 64 * n, 64 * j);
      tma2d(dst + 8192, &maps.g32, fb, f_half, 64 * n);
      tma2d(dst + 12288, &maps.u32, fb, f_half, 64 * n);
    } else if (n == 9 || n == 10 || n >= 34) {
      tma4d(dst, &maps.e, fb, 0, 0, 0, 2 * rb + (n >= 34 ? n - 34 : n - 9));
    } else {
      const int q = n == 8 ? 0 : n - 10;
      tma2d(dst, &maps.g64, fb, f_full + 64 * (q >> 3), 64 * (q & 7));
      tma2d(dst + 8192, &maps.u64, fb, f_full + 64 * (q >> 3), 64 * (q & 7));
    }
  };
  auto x_load = [&](int q) {
    mbar_expect_tx(bars + 8 * (B_FX + q), U);
    tma3d(sb + q * U, &maps.x, bars + 8 * (B_FX + q), 64 * q, 0, 2 * rb);
  };
  if (warp >= 12 && lane == 0) {
    if (warp < 14) {
      const int p = warp - 12;
      mbar_init(bars + 8 * (B_FX + p), 1); mbar_init(bars + 8 * (B_FA + p), 1);
      mbar_init(bars + 8 * (B_FX + p + 2), 1); mbar_init(bars + 8 * (B_FA + p + 2), 1);
      asm volatile("fence.proxy.async.shared::cta;" ::: "memory");
      if (!helper) { x_load(p); ring_load(p); }
    } else if (warp == 14) {
#pragma unroll
      for (int i = 4; i < 8; i++) mbar_init(bars + 8 * (B_FX + i), 1);
#pragma unroll
      for (int i = 4; i < 12; i++) asm volatile("prefetch.tensormap [%0];" ::"l"((const char*)&maps + i * 128) : "memory");
    } else {
#pragma unroll
      for (int i = B_FT; i < NBAR; i++) mbar_init(bars + 8 * i, i < B_EA ? 1 : i < B_T ? 2 : 4);
#pragma unroll
      for (int i = 0; i < 4; i++) mbar_expect_tx(bars + 8 * (B_Z + i), U);
      asm volatile("fence.mbarrier_init.release.cluster;" ::: "memory");
    }
  }
  __syncthreads();
  asm volatile("barrier.cluster.arrive.relaxed.aligned;" ::: "memory");
  if (tid == 64) PROF_EV(38);

  if (warp >= 12) {
    asm volatile("setmaxnreg.dec.sync.aligned.u32 24;");
    if (lane == 0 && !helper) {
      if (warp == 12) PROF_EV(30);
      if (warp < 14) {
#pragma unroll 1
        for (int n = warp - 10; n < 36; n += 2) {
          if (n >= 4) mbar_wait(bars + 8 * (B_EA + (n & 3)), ((n >> 2) & 1) ^ 1);
          else x_load(n);
          ring_load(n);
          if (n >= 3 && n < 7) x_load(n + 1);
        }
      } else if (warp == 15) {
        const unsigned ep1 = ld_x1(&g_epoch[blockIdx.x * 8]) + 1;
        hint_wait(&g_cntX[32 * j], ep1 * 128u); mbar_arrive(bars + 8 * B_HX);
        hint_wait(&g_cntT[32 * j], ep1 * (j == 0 ? 68u : 64u)); mbar_arrive(bars + 8 * B_HT);
#pragma unroll 1
        for (int i = 0; i < 3; i++) { hint_wait(&g_cntP[32 * (rb * 8 + j) + i], ep1 * 8u); mbar_arrive(bars + 8 * (B_HP + i)); }
      } else {
        PROF_EV(31);
        mbar_wait(bars + 8 * (B_FX + 7), 0);
        PROF_EV(32);
        mbar_expect_tx(bars + 8 * B_W, 24576);
        tma4d(sb + OFF_WRAW, &maps.wr, bars + 8 * B_W, 16 * kg, 0, tn, 0);
        tma4d(sb + OFF_WRAW + 12288, &maps.wi, bars + 8 * B_W, 16 * kg, 0, tn, 0);
#pragma unroll 1
        for (int t = 0; t < 8; t++) {
          const int i = t < 3 ? t + 1 : t < 6 ? t - 2 : 0;
          const int col = 64 * (2 * ((q4 + i) & 3) + ((t < 3 || t == 6) ? 1 - rank : rank));
          const uint32_t fb = bars + 8 * (B_FT + (t & 3)), dst = sb + (t & 3) * TB;
          mbar_wait(bars + 8 * (B_ET + (t & 3)), t >> 2);
          mbar_expect_tx(fb, TB);
          tma2d(dst, &maps.d192, fb, col, f_full);
          tma2d(dst + 24576, &maps.d32, fb, col, f_half);
          tma4d(dst + 28672, &maps.fg, fb, col, 0, 0, 4 * j);
        }
      }
    }
  } else if (warp >= 8) {
    asm volatile("setmaxnreg.dec.sync.aligned.u32 88;");
    const int t = tid - 256, w = warp - 8;
    const float scale = 2.0f / (2048.0f * 512.0f);
    const uint32_t ep = ld_x1(&g_epoch[blockIdx.x * 8]);
    if (!helper) {
      uint4 xv[8], gv[2];
#pragma unroll
      for (int i = 0; i < 4; i++) {
        const int r = 16 * j + 4 * w + i;
        const uint4* p = (const uint4*)(x + (size_t)(2 * rb + (r >> 6) + 32 * (r & 63)) * 512) + lane;
        xv[2 * i] = __ldg(p); xv[2 * i + 1] = __ldg(p + 32);
      }
      gv[0] = __ldg((const uint4*)gate_w + lane); gv[1] = __ldg((const uint4*)gate_w + lane + 32);
      const uint32_t tag = (ep + 1) & 1;
      {
        float z[4];
#pragma unroll
        for (int i = 0; i < 4; i++) {
          float a = 0.f;
#pragma unroll
          for (int hh = 0; hh < 2; hh++) {
            const uint4 u = xv[2 * i + hh], v = gv[hh];
            a = fmaf(bf_lo(u.x), bf_lo(v.x), a); a = fmaf(bf_hi(u.x), bf_hi(v.x), a);
            a = fmaf(bf_lo(u.y), bf_lo(v.y), a); a = fmaf(bf_hi(u.y), bf_hi(v.y), a);
            a = fmaf(bf_lo(u.z), bf_lo(v.z), a); a = fmaf(bf_hi(u.z), bf_hi(v.z), a);
            a = fmaf(bf_lo(u.w), bf_lo(v.w), a); a = fmaf(bf_hi(u.w), bf_hi(v.w), a);
          }
#pragma unroll
          for (int o = 16; o; o >>= 1) a += __shfl_xor_sync(0xffffffffu, a, o);
          z[i] = a;
        }
        if (lane < 4) {
          const float zz = lane == 0 ? z[0] : lane == 1 ? z[1] : lane == 2 ? z[2] : z[3];
          asm volatile("st.relaxed.gpu.global.f32 [%0], %1;" ::"l"(g_gate + rb * 128 + 16 * j + 4 * w + lane), "f"(tagf(1.0f / (1.0f + __expf(-zz)), tag)) : "memory");
        }
        if (t == 0) PROF_EV(18);
      }
      if (w == 0) {
        const int c = lane >> 4, jj = 16 * blockIdx.x + (lane & 15), jm = (2048 - jj) & 2047;
        const unsigned short* pr = (const unsigned short*)w_r + 256 * c;
        const unsigned short* pi = (const unsigned short*)w_i + 256 * c;
        const float wr = 0.5f * (bf_lo(__ldg(pr + jj * 257)) + bf_lo(__ldg(pr + jm * 257)));
        const float wi = 0.5f * (bf_lo(__ldg(pi + jj * 257)) - bf_lo(__ldg(pi + jm * 257)));
        st_x2(g_Wh + c * 2048 + jj, tagf(c ? -wi : wr, tag), c ? wr : wi);
        __syncwarp();
        if (lane == 0) hint_add(&g_cntW[0]);
      }
      const int k = 16 * kg + (t & 15), j1 = 8 * tn + (t >> 4);
      {
        const unsigned short* p = (const unsigned short*)(smem + OFF_WRAW) + (t >> 4) * 25 + (t & 15);
        uint32_t wv[32];
        mbar_wait(bars + 8 * B_W, 0);
#pragma unroll
        for (int a = 0; a < 32; a++) wv[a] = (uint32_t)p[a * 192] | ((uint32_t)p[6144 + a * 192] << 16);
        asm volatile("bar.sync 1, 128;" ::: "memory");
#pragma unroll
        for (int a = 0; a < 8; a++) *(uint4*)(smem + OFF_WRAW + (a * 128 + t) * 16) = make_uint4(wv[4 * a], wv[4 * a + 1], wv[4 * a + 2], wv[4 * a + 3]);
      }
      if (t == 0) PROF_EV(11);
      mbar_wait(bars + 8 * B_HX, 0);
      float2 v[32];
      if (t == 0) PROF_EV(22);
      {
        const uint32_t* src = (const uint32_t*)(g_X1p + (size_t)(kg * 8 + tn) * 2048 + ((t >> 3) & 1) * 32 + w * 8 + (t & 7)) + ((t >> 4) & 1);
        const uint32_t chk = (t & 16) ? 0u : 1u;
        uint32_t u[32];
        const uint32_t t0 = (uint32_t)clock();
        for (;;) {
          uint32_t bad = 0;
#pragma unroll
          for (int a = 0; a < 32; a++) u[a] = ld_x1(src + a * 128);
#pragma unroll
          for (int a = 0; a < 32; a++) bad |= u[a] ^ tag;
          if (!__any_sync(0xffffffffu, bad & chk)) break;
          spin_guard(t0);
        }
#pragma unroll
        for (int a = 0; a < 32; a++) v[a] = make_float2(bf_lo(u[a] & ~chk), bf_hi(u[a]));
      }
      if (t == 0) PROF_EV(12);
      dft<-1, 32, 0, 1>(v);
      float2 y[32];
#pragma unroll
      for (int a4 = 0; a4 < 8; a4++) {
        const uint4 ww = *(const uint4*)(smem + OFF_WRAW + (a4 * 128 + t) * 16);
        const uint32_t wq[4] = {ww.x, ww.y, ww.z, ww.w};
#pragma unroll
        for (int e = 0; e < 4; e++) {
          const float2 z = v[brev(4 * a4 + e, 5)];
          const float wr = bf_lo(wq[e]), wi = bf_hi(wq[e]);
          y[4 * a4 + e] = make_float2(fmaf(z.x, wr, -z.y * wi), fmaf(z.x, wi, z.y * wr));
        }
      }
      dft<1, 32, 0, 1>(y);
      if (t == 0) PROF_EV(16);
      {
        uint2* dst = g_T + (size_t)j * 32768 + (kg & 1) * 1024 + j1 * 16 + (t & 15);
#pragma unroll
        for (int a = 0; a < 16; a++) {
          const float2 u0 = y[brev(2 * a, 5)], u1 = y[brev(2 * a + 1, 5)];
          if (k != 0) st_u2(dst + a * 2048, (pack_bf16(u0.x * scale, u0.y * scale) & ~1u) | tag, pack_bf16(u1.x * scale, u1.y * scale));
          if (TPACE && (a & 3) == 3 && a < 15) __nanosleep(TPACE);
        }
        __syncwarp();
        if (lane == 0) hint_add(&g_cntT[32 * j]);
      }
      if (t == 0) PROF_EV(17);
      {
        const uint4* src = (const uint4*)(g_T + (size_t)(j * 16 + rb) * 2048) + t;
        uint4 u[8];
        mbar_wait(bars + 8 * B_HT, 0);
        if (t == 0) PROF_EV(23);
        const uint32_t t0 = (uint32_t)clock();
        for (;;) {
          uint32_t bad = 0;
#pragma unroll
          for (int a = 0; a < 8; a++) u[a] = ld_x4(src + a * 128);
#pragma unroll
          for (int a = 0; a < 8; a++) bad |= (u[a].x ^ tag) | (u[a].z ^ tag);
          if (!__any_sync(0xffffffffu, bad & 1)) break;
          spin_guard(t0);
        }
        const int r = t >> 3, c = t & 7;
#pragma unroll
        for (int a = 0; a < 8; a++) {
          const uint32_t dst = sb + OFF_T + (16 * (a & 3) + r) * 128 + ((((a >> 2) * 4 + (c >> 1)) ^ (r & 7)) << 4) + (c & 1) * 8;
          asm volatile("st.shared.v2.u32 [%0], {%1,%2};" ::"r"(dst), "r"(u[a].x & ~1u), "r"(u[a].z & ~1u) : "memory");
          asm volatile("st.shared.v2.u32 [%0], {%1,%2};" ::"r"(dst + 8192), "r"(u[a].y), "r"(u[a].w) : "memory");
        }
        asm volatile("fence.proxy.async.shared::cta;" ::: "memory");
        __syncwarp();
        if (lane == 0) mbar_arrive(bars + 8 * B_T);
        if (t == 0) PROF_EV(13);
      }
    } else if (w == 0) {
      const uint32_t tag = (ep + 1) & 1;
      const int c = lane >> 4, j1 = 16 * (blockIdx.x - 128) + (lane & 15);
      float2* wf = (float2*)smem;
      float2 v[32];
      hint_wait(&g_cntW[0], (ep + 1) * 128u);
      load32_tagged(v, g_Wh + c * 2048 + j1, 64, tag);
#pragma unroll
      for (int a = 0; a < 32; a++) wf[a * 32 + lane] = v[a];
      if (t == 0) PROF_EV(11);
      hint_wait(&g_cntX[0], (ep + 1) * 128u);
      load32_tagged(v, g_X1s + c * 2048 + j1, 64, tag);
      if (t == 0) PROF_EV(12);
      dft<-1, 32, 0, 1>(v);
      float2 y[32];
#pragma unroll
      for (int a = 0; a < 32; a++) {
        const float2 z = v[brev(a, 5)], wv = wf[a * 32 + lane];
        y[a] = make_float2(fmaf(z.x, wv.x, -z.y * wv.y), fmaf(z.x, wv.y, z.y * wv.x));
      }
      dft<1, 32, 0, 1>(y);
      if (t == 0) PROF_EV(16);
#pragma unroll
      for (int a = 0; a < 8; a++) {
        uint32_t pk[2];
#pragma unroll
        for (int e = 0; e < 2; e++) {
          const float2 u0 = y[brev(4 * a + e, 5)], u1 = y[brev(4 * a + 2 + e, 5)];
          const float2 keep = c ? u1 : u0, give = c ? u0 : u1;
          const float ox = __shfl_xor_sync(0xffffffffu, give.x, 16), oy = __shfl_xor_sync(0xffffffffu, give.y, 16);
          pk[e] = pack_bf16((keep.x + ox) * (0.5f * scale), (keep.y + oy) * (0.5f * scale));
        }
        st_u2(g_T + (2 * a + c) * 2048 + j1 * 16, (pk[0] & ~1u) | tag, pk[1]);
      }
      __syncwarp();
      if (t == 0) { hint_add(&g_cntT[0]); g_epoch[blockIdx.x * 8] = ep + 1; PROF_EV(13); }
    }
  } else {
    asm volatile("setmaxnreg.inc.sync.aligned.u32 200;");
    if (!helper) {
      const int wg = warp >> 2, w = warp & 3, g = lane >> 2, q = lane & 3;
      const bool elect = (tid & 127) == 0;
      const uint32_t ep = ld_x1(&g_epoch[blockIdx.x * 8]);
      float c1[64], cA[64], c2[64], ci[64], ct[64];
      const int zero = blockIdx.x >> 16;
      uint32_t h[56], yf[16];
      const uint32_t d0 = (sb & 0x3FFFF) >> 4;
      const uint32_t dK = d0 | (1u << 16), dN = d0 | (512u << 16), dM = d0 | (256u << 16);
      const uint32_t dX = dK + wg * 512;
      constexpr uint32_t RING = OFF_RING >> 4;
      auto waitA = [&](int n) { mbar_wait(bars + 8 * (B_FA + (n & 3)), (n >> 2) & 1); };
      auto freeA = [&](int n) { if (elect) mbar_arrive(bars + 8 * (B_EA + (n & 3))); };

      auto c1_step = [&](auto first, int kb) {
        mbar_wait(bars + 8 * (B_FX + kb), 0); waitA(kb);
        wg_fence();
        const uint64_t dx = d128(dX + kb * 1024), df = d128(dK + RING + (kb & 3) * 1024), dm = d64(dM + RING + 512 + (kb & 3) * 1024);
        mma_ss64<0, 0, decltype(first)::value>(c1, df, dx);
        mma_ss64<32, 1, decltype(first)::value>(c1, dx, dm);
#pragma unroll
        for (int k = 1; k < 4; k++) {
          mma_ss64<0, 0, 1>(c1, df + k * 2, dx + k * 2);
          mma_ss64<32, 1, 1>(c1, dx + k * 2, dm + k * 64);
        }
        wg_commit();
      };
      c1_step(IC<0>(), 0);
      if (tid == 0) PROF_EV(1);
#pragma unroll 1
      for (int kb = 1; kb < 8; kb++) { c1_step(IC<1>(), kb); wg_wait<1>(); freeA(kb - 1); }
      auto ffn_step = [&](auto first, float (&acc)[64], int n, int kb) {
        waitA(n);
        wg_fence();
        const uint64_t dx = d128(dX + kb * 1024), db = d128(dN + RING + (n & 3) * 1024);
        mma_ss128<0, 1, decltype(first)::value>(acc, dx, db, zero);
#pragma unroll
        for (int k = 1; k < 4; k++) mma_ss128<0, 1, 1>(acc, dx + k * 2, db + k * 128);
        wg_commit();
        wg_wait<1>();
      };
      const uint32_t tag = (ep + 1) & 1;
      ffn_step(IC<0>(), c2, 8, 0);
      freeA(7);
      fence_regs<0, 64>(c1);
      if (tid == 0) PROF_EV(2);
#pragma unroll
      for (int i = 0; i < 16; i++) yf[i] = pack_pin(c1[2 * i], c1[2 * i + 1]);
      float hm[16];
#pragma unroll
      for (int i = 0; i < 16; i++) hm[i] = fmaxf(c1[32 + i], 0.f) * c1[48 + i];
      fence_regs<0, 16>(hm);
      {
        waitA(9); waitA(10);
        const uint64_t de = d128(dN + RING + (1 + wg) * 1024);
        wg_fence();
        mma_rs128<0, 1, 0>(cA, yf[0], yf[1], yf[2], yf[3], de);
#pragma unroll
        for (int k = 1; k < 4; k++) mma_rs128<0, 1, 1>(cA, yf[4 * k], yf[4 * k + 1], yf[4 * k + 2], yf[4 * k + 3], de + k * 128);
        wg_commit();
        wg_wait<1>();
        freeA(8);
        ffn_step(IC<1>(), c2, 11, 1);
        freeA(9); freeA(10);
        fence_regs<0, 64>(cA);
        if (tid == 0) PROF_EV(19);
        const int s0 = 2 * rb + wg;
        uint2* dst = g_X1p + ((size_t)((2 * j + (w >> 1)) * 8) * 32 + s0) * 64 + (w & 1) * 32 + q * 8 + g;
        auto x1_store = [&](int n0, int n1) {
#pragma unroll
          for (int n = n0; n < n1; n++)
            st_u2(dst + n * 2048, (pack_bf16(cA[4 * n] - cA[34 + 4 * n], cA[32 + 4 * n] + cA[4 * n + 2]) & ~1u) | tag,
                  pack_bf16(cA[4 * n + 1] - cA[35 + 4 * n], cA[33 + 4 * n] + cA[4 * n + 3]));
        };
        if (j == 0 && w == 0 && g == 0) {
#pragma unroll
          for (int n = 0; n < 8; n++) {
#pragma unroll
            for (int e = 0; e < 2; e++) {
              st_x2(g_X1s + s0 * 64 + 8 * n + 2 * q + e, tagf(cA[4 * n + e], tag), cA[32 + 4 * n + e]);
              st_x2(g_X1s + (32 + s0) * 64 + 8 * n + 2 * q + e, tagf(cA[4 * n + 2 + e], tag), cA[34 + 4 * n + e]);
            }
          }
        }
        __syncwarp();
        x1_store(0, 3);
        ffn_step(IC<1>(), c2, 12, 2); freeA(11);
        x1_store(3, 6);
        ffn_step(IC<1>(), c2, 13, 3); freeA(12);
        x1_store(6, 8);
        __syncwarp();
        if (lane == 0) hint_add(&g_cntX[32 * j]);
        if (tid == 0) PROF_EV(3);
      }
      const float* gp = g_gate + rb * 128 + wg * 64 + w * 16 + g;
      uint32_t gb0 = ld_x1(gp), gb1 = ld_x1(gp + 8);
#pragma unroll 1
      for (int kb = 4; kb < 8; kb++) { ffn_step(IC<1>(), c2, 10 + kb, kb); freeA(9 + kb); }
      ffn_step(IC<2>(), cA, 18, 0); freeA(17);
      fence_regs<0, 64>(c2);
      if (tid == 0) PROF_EV(4);
      {
        const uint32_t t0 = (uint32_t)clock();
        while (__any_sync(0xffffffffu, ((gb0 ^ tag) | (gb1 ^ tag)) & 1)) { gb0 = ld_x1(gp); gb1 = ld_x1(gp + 8); spin_guard(t0); }
      }
      const float g0 = __uint_as_float(gb0 & ~1u), g1 = __uint_as_float(gb1 & ~1u);
      const float o0 = 1.0f - g0, o1 = 1.0f - g1;
      auto glu = [&](float (&acc)[64], int ho) {
#pragma unroll
        for (int i = 0; i < 16; i++) {
          const float o = (i & 1) ? o1 : o0;
          h[ho + i] = pack_pin(fmaxf(acc[2 * i], 0.f) * acc[32 + 2 * i] * o, fmaxf(acc[2 * i + 1], 0.f) * acc[33 + 2 * i] * o);
        }
      };
#pragma unroll
      for (int i = 0; i < 8; i++) h[48 + i] = pack_pin(hm[2 * i] * ((i & 1) ? o1 : o0), hm[2 * i + 1] * ((i & 1) ? o1 : o0));
      glu(c2, 0);
#pragma unroll 1
      for (int kb = 1; kb < 8; kb++) { ffn_step(IC<1>(), cA, 18 + kb, kb); freeA(17 + kb); }
      ffn_step(IC<2>(), c2, 26, 0); freeA(25);
      fence_regs<0, 64>(cA);
      if (tid == 0) PROF_EV(5);
      glu(cA, 16);
#pragma unroll 1
      for (int kb = 1; kb < 8; kb++) {
        ffn_step(IC<1>(), c2, 26 + kb, kb); freeA(25 + kb);
        if (elect && kb >= 3 && (kb & 1)) mbar_arrive(bars + 8 * (B_ET + ((kb - 3) >> 1)));
      }
      wg_wait<0>();
      if (elect) mbar_arrive(bars + 8 * (B_ET + 3));
      fence_regs<0, 64>(c2);
      glu(c2, 32);
      waitA(34 + wg);
      if (tid == 0) PROF_EV(6);
      mbar_wait(bars + 8 * B_T, 0);
      if (tid == 0) PROF_EV(7);
      wg_fence();
      {
        const uint64_t dt = d128(dN + (OFF_T >> 4) + wg * 512), de = d128(dK + RING + (2 + wg) * 1024);
        mma_ss64<0, 1, 0>(ci, de, dt);
        mma_ss64<32, 1, 0>(ci, de + 512, dt);
#pragma unroll
        for (int k = 1; k < 4; k++) {
          mma_ss64<0, 1, 1>(ci, de + k * 2, dt + k * 128);
          mma_ss64<32, 1, 1>(ci, de + (512 + k * 2), dt + k * 128);
        }
      }
      wg_commit();

      auto head = [&](auto off, int t) {
        constexpr int O = decltype(off)::value;
        mbar_wait(bars + 8 * (B_FT + (t & 3)), t >> 2);
        const uint64_t db = d128(dN + (t & 3) * (TB >> 4));
        wg_fence();
        mma_rs64<O, 1, 0>(ct, h[0], h[1], h[2], h[3], db);
#pragma unroll
        for (int k = 1; k < 6; k++) mma_rs64<O, 1, 1>(ct, h[4 * k], h[4 * k + 1], h[4 * k + 2], h[4 * k + 3], db + k * 128);
        wg_commit();
        wg_wait<1>();
      };
      auto rest = [&](auto off, int t) {
        constexpr int O = decltype(off)::value;
        const uint64_t db = d128(dN + (t & 3) * (TB >> 4));
        wg_fence();
#pragma unroll
        for (int k = 6; k < 14; k++) mma_rs64<O, 1, 1>(ct, h[4 * k], h[4 * k + 1], h[4 * k + 2], h[4 * k + 3], db + k * 128);
#pragma unroll
        for (int k = 0; k < 4; k++) mma_rs64<O, 1, 1>(ct, yf[4 * k], yf[4 * k + 1], yf[4 * k + 2], yf[4 * k + 3], db + (14 + k) * 128);
        wg_commit();
      };
      auto freeT = [&](int t) { if (elect) mbar_arrive(bars + 8 * (B_ET + t)); };
      const uint32_t peerZ = mapa(sb + OFF_Z + tid * 16, rank ^ 1), peerB = mapa(bars + 8 * B_Z, rank ^ 1);
      auto send_peer = [&](auto off, int z) {
        constexpr int O = decltype(off)::value;
        fence_regs<O, 32>(ct);
#pragma unroll
        for (int i = 0; i < 4; i++)
          asm volatile("st.async.weak.shared::cluster.mbarrier::complete_tx::bytes.v4.b32 [%0], {%1,%2,%3,%4}, [%5];" ::"r"(peerZ + z * U + i * 4096),
                       "r"(pack_bf16(ct[O + 8 * i], ct[O + 8 * i + 1])), "r"(pack_bf16(ct[O + 8 * i + 2], ct[O + 8 * i + 3])),
                       "r"(pack_bf16(ct[O + 8 * i + 4], ct[O + 8 * i + 5])), "r"(pack_bf16(ct[O + 8 * i + 6], ct[O + 8 * i + 7])), "r"(peerB + 8 * z) : "memory");
      };
      auto send_grid = [&](auto off, int z) {
        constexpr int O = decltype(off)::value;
        fence_regs<O, 32>(ct);
        mbar_wait(bars + 8 * (B_Z + z), 0);
        uint4* dst = g_part + (size_t)((rb * 8 + 2 * ((q4 + z + 1) & 3) + rank) * 3 + z) * 1024 + tid;
#pragma unroll
        for (int i = 0; i < 4; i++) {
          const uint4 p = *(const uint4*)(smem + OFF_Z + z * U + i * 4096 + tid * 16);
          st_x4(dst + i * 256, (pack_bf16(ct[O + 8 * i] + bf_lo(p.x), ct[O + 8 * i + 1] + bf_hi(p.x)) & ~1u) | tag,
                pack_bf16(ct[O + 8 * i + 2] + bf_lo(p.y), ct[O + 8 * i + 3] + bf_hi(p.y)),
                pack_bf16(ct[O + 8 * i + 4] + bf_lo(p.z), ct[O + 8 * i + 5] + bf_hi(p.z)),
                pack_bf16(ct[O + 8 * i + 6] + bf_lo(p.w), ct[O + 8 * i + 7] + bf_hi(p.w)));
        }
        __syncwarp();
        if (lane == 0) hint_add(&g_cntP[32 * (rb * 8 + 2 * ((q4 + z + 1) & 3) + rank) + z]);
      };
      asm volatile("barrier.cluster.wait.aligned;" ::: "memory");
      head(IC<0>(), 0);
      if (elect) asm volatile("mbarrier.arrive.shared::cluster.b64 _, [%0];" ::"r"(mapa(bars + 8 * B_RDY, rank ^ 1)) : "memory");
      fence_regs<0, 64>(ci);
#pragma unroll
      for (int i = 0; i < 16; i++) {
        const float gg = (i & 1) ? g1 : g0;
        yf[i] = pack_pin((ci[2 * i] + ci[33 + 2 * i]) * gg, (ci[2 * i + 1] - ci[32 + 2 * i]) * gg);
      }
      rest(IC<0>(), 0);
      if (tid == 0) PROF_EV(8);
      head(IC<32>(), 1); freeT(0); mbar_wait(bars + 8 * B_RDY, 0); send_peer(IC<0>(), 0); rest(IC<32>(), 1);
      head(IC<0>(), 2); freeT(1); send_peer(IC<32>(), 1); rest(IC<0>(), 2);
      head(IC<32>(), 3); freeT(2); send_peer(IC<0>(), 2); rest(IC<32>(), 3);
      head(IC<0>(), 4); freeT(3); send_grid(IC<32>(), 0); rest(IC<0>(), 4);
      head(IC<32>(), 5); send_grid(IC<0>(), 1); rest(IC<32>(), 5);
      head(IC<0>(), 6); send_grid(IC<32>(), 2); rest(IC<0>(), 6);
      head(IC<32>(), 7); send_peer(IC<0>(), 3);
      {
        const uint4* src = g_part + (size_t)(rb * 8 + j) * 3 * 1024 + tid;
        uint4 pv[12];
        mbar_wait(bars + 8 * (B_HP + 1), 0);
#pragma unroll
        for (int i = 0; i < 8; i++) pv[i] = ld_x4(src + i * 256);
        rest(IC<32>(), 7);
        if (tid == 0) PROF_EV(9);
        mbar_wait(bars + 8 * (B_HP + 2), 0);
        if (tid == 0) PROF_EV(24);
#pragma unroll
        for (int i = 8; i < 12; i++) pv[i] = ld_x4(src + i * 256);
        const uint32_t t0 = (uint32_t)clock();
        for (;;) {
          uint32_t bad = 0;
#pragma unroll
          for (int i = 0; i < 12; i++) bad |= pv[i].x ^ tag;
          if (!__any_sync(0xffffffffu, bad & 1)) break;
#pragma unroll
          for (int i = 0; i < 12; i++) pv[i] = ld_x4(src + i * 256);
          spin_guard(t0);
        }
        if (tid == 0) PROF_EV(14);
        float sum[32];
#pragma unroll
        for (int i = 0; i < 4; i++) {
          const uint32_t a[4] = {pv[i].x & ~1u, pv[i].y, pv[i].z, pv[i].w}, b[4] = {pv[4 + i].x & ~1u, pv[4 + i].y, pv[4 + i].z, pv[4 + i].w},
                         c[4] = {pv[8 + i].x & ~1u, pv[8 + i].y, pv[8 + i].z, pv[8 + i].w};
#pragma unroll
          for (int e = 0; e < 4; e++) {
            sum[8 * i + 2 * e] = bf_lo(a[e]) + bf_lo(b[e]) + bf_lo(c[e]);
            sum[8 * i + 2 * e + 1] = bf_hi(a[e]) + bf_hi(b[e]) + bf_hi(c[e]);
          }
        }
        mbar_wait(bars + 8 * (B_Z + 3), 0);
#pragma unroll
        for (int i = 0; i < 4; i++) {
          const uint4 p = *(const uint4*)(smem + OFF_Z + 3 * U + i * 4096 + tid * 16);
          const uint32_t a[4] = {p.x, p.y, p.z, p.w};
#pragma unroll
          for (int e = 0; e < 4; e++) { sum[8 * i + 2 * e] += bf_lo(a[e]); sum[8 * i + 2 * e + 1] += bf_hi(a[e]); }
        }
        wg_wait<0>();
        fence_regs<32, 32>(ct);
#pragma unroll
        for (int i = 0; i < 32; i++) sum[i] += ct[32 + i];
        const uint32_t stg = sb + OFF_T + warp * 2048;
        const int mr = (lane & 7) + ((lane >> 3) & 1) * 8, mc = lane >> 4;
#pragma unroll
        for (int i = 0; i < 4; i++) {
          const uint32_t a = stg + mr * 128 + (((2 * i + mc) ^ (mr & 7)) << 4);
          asm volatile("stmatrix.sync.aligned.m8n8.x4.shared.b16 [%0], {%1,%2,%3,%4};" ::"r"(a), "r"(pack_bf16(sum[8 * i], sum[8 * i + 1])),
                       "r"(pack_bf16(sum[8 * i + 2], sum[8 * i + 3])), "r"(pack_bf16(sum[8 * i + 4], sum[8 * i + 5])),
                       "r"(pack_bf16(sum[8 * i + 6], sum[8 * i + 7])) : "memory");
        }
        __syncwarp();
#pragma unroll
        for (int i = 0; i < 4; i++) {
          const int r = 4 * i + (lane >> 3), c = lane & 7;
          const uint4 v = *(const uint4*)(smem + OFF_T + warp * 2048 + r * 128 + ((c ^ (r & 7)) << 4));
          *(uint4*)(out + (size_t)(2 * rb + wg + 32 * (16 * w + r)) * 512 + 64 * j + 8 * c) = v;
        }
      }
      if (tid == 0) { g_epoch[blockIdx.x * 8] = ep + 1; PROF_EV(15); PROF_CK(41); }
    }
  }
}

typedef CUresult (*EncodeFn)(CUtensorMap*, CUtensorMapDataType, cuuint32_t, void*, const cuuint64_t*, const cuuint64_t*, const cuuint32_t*,
                             const cuuint32_t*, CUtensorMapInterleave, CUtensorMapSwizzle, CUtensorMapL2promotion, CUtensorMapFloatOOBfill);

static void encode(EncodeFn f, CUtensorMap* m, const void* base, int rank, const cuuint64_t* dims, const cuuint64_t* strides, const cuuint32_t* box,
                   CUtensorMapSwizzle sw) {
  cuuint32_t es[5] = {1, 1, 1, 1, 1};
  f(m, CU_TENSOR_MAP_DATA_TYPE_BFLOAT16, rank, (void*)base, dims, strides, box, es, CU_TENSOR_MAP_INTERLEAVE_NONE, sw,
    CU_TENSOR_MAP_L2_PROMOTION_L2_128B, CU_TENSOR_MAP_FLOAT_OOB_FILL_NONE);
}

extern "C" void kernel_launch(void* const* d_in, const int* in_sizes, int n_in, void* d_out, int out_size) {
  (void)in_sizes; (void)n_in; (void)out_size;
  const __nv_bfloat16* x = (const __nv_bfloat16*)d_in[0];
  const __nv_bfloat16* w_r = (const __nv_bfloat16*)d_in[1];
  const __nv_bfloat16* w_i = (const __nv_bfloat16*)d_in[2];
  const __nv_bfloat16* Wg = (const __nv_bfloat16*)d_in[4];
  const __nv_bfloat16* Wu = (const __nv_bfloat16*)d_in[5];
  const __nv_bfloat16* Wd = (const __nv_bfloat16*)d_in[6];
  const __nv_bfloat16* gw = (const __nv_bfloat16*)d_in[7];

  void* fp = nullptr; cudaDriverEntryPointQueryResult qr;
  cudaGetDriverEntryPoint("cuTensorMapEncodeTiled", &fp, cudaEnableDefault, &qr);
  EncodeFn enc = (EncodeFn)fp;
  void *pFT, *pET;
  cudaGetSymbolAddress(&pFT, g_FT); cudaGetSymbolAddress(&pET, g_ET);

  Maps mp;
  const CUtensorMapSwizzle S128 = CU_TENSOR_MAP_SWIZZLE_128B, S64 = CU_TENSOR_MAP_SWIZZLE_64B;
  { cuuint64_t d[3] = {512, 64, 32}, s[2] = {32768, 1024}; cuuint32_t b[3] = {64, 64, 2}; encode(enc, &mp.x, x, 3, d, s, b, S128); }
  { cuuint64_t d[2] = {512, 512}, s[1] = {1024}; cuuint32_t b[2] = {64, 64}; encode(enc, &mp.ft, pFT, 2, d, s, b, S128); }
  { cuuint64_t d[4] = {512, 2, 8, 32}, s[3] = {8192, 1024, 16384}; cuuint32_t b[4] = {64, 2, 8, 4}; encode(enc, &mp.fg, pFT, 4, d, s, b, S128); }
  { cuuint64_t d[4] = {64, 64, 2, 32}, s[3] = {8192, 128, 256}; cuuint32_t b[4] = {64, 64, 2, 1}; encode(enc, &mp.e, pET, 4, d, s, b, S128); }
  { cuuint64_t d[2] = {1792, 512}, s[1] = {3584}; cuuint32_t b[2] = {64, 64}, b2[2] = {32, 64};
    encode(enc, &mp.g64, Wg, 2, d, s, b, S128); encode(enc, &mp.u64, Wu, 2, d, s, b, S128);
    encode(enc, &mp.g32, Wg, 2, d, s, b2, S64); encode(enc, &mp.u32, Wu, 2, d, s, b2, S64); }
  { cuuint64_t d[2] = {512, 1792}, s[1] = {1024}; cuuint32_t b[2] = {64, 192}, b2[2] = {64, 32};
    encode(enc, &mp.d192, Wd, 2, d, s, b, S128); encode(enc, &mp.d32, Wd, 2, d, s, b2, S128); }

  { cuuint64_t d[4] = {264, 8, 8, 32}, s[3] = {512, 4112, 32896}; cuuint32_t b[4] = {24, 8, 1, 32};
    encode(enc, &mp.wr, w_r, 4, d, s, b, CU_TENSOR_MAP_SWIZZLE_NONE); encode(enc, &mp.wi, w_i, 4, d, s, b, CU_TENSOR_MAP_SWIZZLE_NONE); }

  cudaFuncSetAttribute(fused_kernel, cudaFuncAttributeMaxDynamicSharedMemorySize, SMEM_BYTES);
  fused_kernel<<<NCTA, 512, SMEM_BYTES>>>(mp, x, w_r, w_i, gw, Wd, (__nv_bfloat16*)d_out);
}
```

```cpp
#include <cuda_runtime.h>
#include <cuda_bf16.h>
#include <cuda.h>
#include <stdint.h>

namespace tbl {
constexpr double PI = 3.14159265358979323846264338327950288;
constexpr double sin_s(double x) { double t = x, s = x; for (int n = 1; n < 12; n++) { t *= -x * x / ((2 * n) * (2 * n + 1)); s += t; } return s; }
constexpr double cos_s(double x) { double t = 1, s = 1; for (int n = 1; n < 12; n++) { t *= -x * x / ((2 * n - 1) * (2 * n)); s += t; } return s; }
constexpr double cos2048(int m) {
  m &= 2047; if (m > 1024) m = 2048 - m;
  bool neg = false; if (m > 512) { m = 1024 - m; neg = true; }
  double v = (m <= 256) ? cos_s(2 * PI * m / 2048) : sin_s(2 * PI * (512 - m) / 2048);
  return neg ? -v : v;
}
constexpr uint16_t to_bf16(double v) {
  if (v == 0) return 0;
  uint16_t s = 0; if (v < 0) { s = 0x8000; v = -v; }
  int e = 0; while (v >= 2) { v /= 2; e++; } while (v < 1) { v *= 2; e--; }
  double m = (v - 1) * 128; int mi = (int)m; double fr = m - mi;
  if (fr > 0.5 || (fr == 0.5 && (mi & 1))) mi++;
  if (mi == 128) { mi = 0; e++; }
  return (uint16_t)(s | ((e + 127) << 7) | mi);
}
struct CosT { uint16_t v[2048]; constexpr CosT() : v() { for (int i = 0; i < 2048; i++) v[i] = to_bf16(cos2048(i)); } };
struct alignas(1024) FT {
  uint16_t v[512 * 512];
  constexpr FT() : v() {
    CosT c;
    for (int r = 0; r < 512; r++) {
      int k = (r >> 4) * 8 + (r & 7), e = (r >> 3) & 1;
      int mul = 4 * k, add = e ? 512 : 0;
      if (k == 0 && e == 1) { mul = 1024; add = 0; }
      for (int d = 0; d < 512; d++) v[r * 512 + d] = c.v[(d * mul + add) & 2047];
    }
  }
};
struct alignas(1024) ET {
  uint16_t v[2048 * 128];
  constexpr ET() : v() {
    CosT c;
    for (int s = 0; s < 2048; s++)
      for (int j = 0; j < 64; j++) { v[s * 128 + j] = c.v[(s * j) & 2047]; v[s * 128 + 64 + j] = c.v[(s * j + 512) & 2047]; }
  }
};
template <int A> struct W32 {
  static constexpr float c = (float)cos2048(A * 64);
  static constexpr float s = (float)cos2048(A * 64 - 512);
};
}

__device__ constexpr tbl::FT g_FT = tbl::FT();
__device__ constexpr tbl::ET g_ET = tbl::ET();

__device__ __align__(1024) uint2 g_X1p[128 * 32 * 64];
__device__ __align__(1024) float2 g_X1s[2 * 32 * 64];
__device__ __align__(1024) uint2 g_T[8 * 16 * 2 * 64 * 16];
__device__ __align__(1024) uint4 g_part[128 * 3 * 1024];
__device__ __align__(16) float g_gate[16 * 128];
__device__ __align__(16) float2 g_Wh[2 * 2048];
__device__ unsigned g_epoch[132 * 8];
__device__ unsigned g_cntX[8 * 32], g_cntT[8 * 32], g_cntP[128 * 32], g_cntW[32];
#define PROF_EV(i) do {} while (0)
#define PROF_CK(i) do {} while (0)

__device__ __forceinline__ uint32_t smem_u32(const void* p) { return (uint32_t)__cvta_generic_to_shared(p); }
__device__ __forceinline__ void mbar_init(uint32_t bar, uint32_t cnt) { asm volatile("mbarrier.init.shared::cta.b64 [%0], %1;" ::"r"(bar), "r"(cnt)); }
__device__ __forceinline__ void mbar_expect_tx(uint32_t bar, uint32_t bytes) { asm volatile("mbarrier.arrive.expect_tx.shared::cta.b64 _, [%0], %1;" ::"r"(bar), "r"(bytes) : "memory"); }
__device__ __forceinline__ void mbar_arrive(uint32_t bar) { asm volatile("mbarrier.arrive.shared::cta.b64 _, [%0];" ::"r"(bar) : "memory"); }
__device__ __forceinline__ bool mbar_try(uint32_t bar, uint32_t parity) {
  uint32_t ok;
  asm volatile("{\n.reg .pred p;\nmbarrier.try_wait.parity.shared::cta.b64 p, [%1], %2;\nselp.u32 %0, 1, 0, p;\n}" : "=r"(ok) : "r"(bar), "r"(parity) : "memory");
  return ok;
}
__device__ __forceinline__ void mbar_wait(uint32_t bar, uint32_t parity) {
  if (mbar_try(bar, parity)) return;
  const uint32_t t0 = (uint32_t)clock();
  while (!mbar_try(bar, parity)) { if ((uint32_t)clock() - t0 > (1u << 30)) __trap(); }
}
__device__ __forceinline__ void spin_guard(uint32_t t0) { if ((uint32_t)clock() - t0 > (1u << 30)) __trap(); }
__device__ __forceinline__ float tagf(float v, uint32_t tag) { return __uint_as_float((__float_as_uint(v) & ~1u) | tag); }
__device__ __forceinline__ float untag(float v) { return __uint_as_float(__float_as_uint(v) & ~1u); }
__device__ __forceinline__ void st_x2(float2* p, float a, float b) { asm volatile("st.relaxed.gpu.global.v2.f32 [%0], {%1,%2};" ::"l"(p), "f"(a), "f"(b) : "memory"); }
__device__ __forceinline__ float2 ld_x2(const float2* p) { float2 v; asm volatile("ld.relaxed.gpu.global.v2.f32 {%0,%1}, [%2];" : "=f"(v.x), "=f"(v.y) : "l"(p) : "memory"); return v; }
__device__ __forceinline__ void st_u2(uint2* p, uint32_t a, uint32_t b) { asm volatile("st.relaxed.gpu.global.v2.u32 [%0], {%1,%2};" ::"l"(p), "r"(a), "r"(b) : "memory"); }
__device__ __forceinline__ void prefetch2d(const CUtensorMap* m, int c0, int c1) { asm volatile("cp.async.bulk.prefetch.tensor.2d.L2.global [%0, {%1, %2}];" ::"l"(m), "r"(c0), "r"(c1) : "memory"); }
__device__ __forceinline__ void prefetch1d(const void* p, uint32_t bytes) { asm volatile("cp.async.bulk.prefetch.L2.global [%0], %1;" ::"l"(p), "r"(bytes) : "memory"); }
__device__ __forceinline__ uint32_t ld_x1(const void* p) { uint32_t v; asm volatile("ld.relaxed.gpu.global.u32 %0, [%1];" : "=r"(v) : "l"(p) : "memory"); return v; }
__device__ __forceinline__ uint4 ld_x4(const void* p) { uint4 v; asm volatile("ld.relaxed.gpu.global.v4.u32 {%0,%1,%2,%3}, [%4];" : "=r"(v.x), "=r"(v.y), "=r"(v.z), "=r"(v.w) : "l"(p) : "memory"); return v; }
__device__ __forceinline__ void st_x4(void* p, uint32_t a, uint32_t b, uint32_t c, uint32_t d) { asm volatile("st.relaxed.gpu.global.v4.u32 [%0], {%1,%2,%3,%4};" ::"l"(p), "r"(a), "r"(b), "r"(c), "r"(d) : "memory"); }
__device__ __forceinline__ uint32_t mapa(uint32_t a, uint32_t cta) { uint32_t r; asm volatile("mapa.shared::cluster.u32 %0, %1, %2;" : "=r"(r) : "r"(a), "r"(cta)); return r; }
__device__ __forceinline__ void hint_add(unsigned* p) { asm volatile("red.relaxed.gpu.global.add.u32 [%0], 1;" ::"l"(p) : "memory"); }
__device__ __forceinline__ void hint_wait(const unsigned* p, unsigned target) {
  const uint32_t t0 = (uint32_t)clock();
  while ((int)(ld_x1(p) - target) < 0) spin_guard(t0);
}
__device__ __forceinline__ void load32_tagged(float2 (&v)[32], const float2* src, int stride, uint32_t tag) {
  const uint32_t t0 = (uint32_t)clock();
  for (;;) {
    uint32_t bad = 0;
#pragma unroll
    for (int a = 0; a < 32; a++) v[a] = ld_x2(src + a * stride);
#pragma unroll
    for (int a = 0; a < 32; a++) bad |= __float_as_uint(v[a].x) ^ tag;
    if (!__any_sync(0xffffffffu, bad & 1)) break;
    spin_guard(t0);
  }
#pragma unroll
  for (int a = 0; a < 32; a++) v[a].x = untag(v[a].x);
}
__device__ __forceinline__ void tma2d(uint32_t dst, const CUtensorMap* m, uint32_t bar, int c0, int c1) {
  asm volatile("cp.async.bulk.tensor.2d.shared::cluster.global.mbarrier::complete_tx::bytes [%0], [%1, {%3, %4}], [%2];" ::"r"(dst), "l"(m), "r"(bar), "r"(c0), "r"(c1) : "memory");
}
__device__ __forceinline__ void tma3d(uint32_t dst, const CUtensorMap* m, uint32_t bar, int c0, int c1, int c2) {
  asm volatile("cp.async.bulk.tensor.3d.shared::cluster.global.mbarrier::complete_tx::bytes [%0], [%1, {%3, %4, %5}], [%2];" ::"r"(dst), "l"(m), "r"(bar), "r"(c0), "r"(c1), "r"(c2) : "memory");
}
__device__ __forceinline__ void tma4d(uint32_t dst, const CUtensorMap* m, uint32_t bar, int c0, int c1, int c2, int c3) {
  asm volatile("cp.async.bulk.tensor.4d.shared::cluster.global.mbarrier::complete_tx::bytes [%0], [%1, {%3, %4, %5, %6}], [%2];" ::"r"(dst), "l"(m), "r"(bar), "r"(c0), "r"(c1), "r"(c2), "r"(c3) : "memory");
}
__device__ __forceinline__ void wg_fence() { asm volatile("wgmma.fence.sync.aligned;" ::: "memory"); }
__device__ __forceinline__ void wg_commit() { asm volatile("wgmma.commit_group.sync.aligned;" ::: "memory"); }
template <int N> __device__ __forceinline__ void wg_wait() { asm volatile("wgmma.wait_group.sync.aligned %0;" ::"n"(N) : "memory"); }
template <int O, int N, int NN> __device__ __forceinline__ void fence_regs(float (&d)[NN]) {
#pragma unroll
  for (int i = 0; i < N; i++) asm volatile("" : "+f"(d[O + i])::"memory");
}
__device__ __forceinline__ uint32_t pack_bf16(float lo, float hi) {
  uint32_t r; asm("cvt.rn.bf16x2.f32 %0, %1, %2;" : "=r"(r) : "f"(hi), "f"(lo)); return r;
}
__device__ __forceinline__ uint32_t pack_pin(float lo, float hi) {
  uint32_t r; asm volatile("cvt.rn.bf16x2.f32 %0, %1, %2;" : "=r"(r) : "f"(hi), "f"(lo) : "memory"); return r;
}
__device__ __forceinline__ float bf_lo(uint32_t u) { return __uint_as_float(u << 16); }
__device__ __forceinline__ float bf_hi(uint32_t u) { return __uint_as_float(u & 0xffff0000u); }

__device__ __forceinline__ uint64_t d128(uint32_t lo) { uint64_t d; asm("mov.b64 %0, {%1, 0x40000040};" : "=l"(d) : "r"(lo)); return d; }
__device__ __forceinline__ uint64_t d64(uint32_t lo) { uint64_t d; asm("mov.b64 %0, {%1, 0x80000020};" : "=l"(d) : "r"(lo)); return d; }
template<int O,int TB,int ACC,int NN> __device__ __forceinline__ void mma_ss64(float (&d)[NN], uint64_t da, uint64_t db, int sd = 0){
  if constexpr (ACC == 1) asm volatile("wgmma.mma_async.sync.aligned.m64n64k16.f32.bf16.bf16 {%0,%1,%2,%3,%4,%5,%6,%7,%8,%9,%10,%11,%12,%13,%14,%15,%16,%17,%18,%19,%20,%21,%22,%23,%24,%25,%26,%27,%28,%29,%30,%31}, %32, %33, 1, 1, 1, 0, %34;"
   : "+f"(d[O+0]), "+f"(d[O+1]), "+f"(d[O+2]), "+f"(d[O+3]), "+f"(d[O+4]), "+f"(d[O+5]), "+f"(d[O+6]), "+f"(d[O+7]), "+f"(d[O+8]), "+f"(d[O+9]), "+f"(d[O+10]), "+f"(d[O+11]), "+f"(d[O+12]), "+f"(d[O+13]), "+f"(d[O+14]), "+f"(d[O+15]), "+f"(d[O+16]), "+f"(d[O+17]), "+f"(d[O+18]), "+f"(d[O+19]), "+f"(d[O+20]), "+f"(d[O+21]), "+f"(d[O+22]), "+f"(d[O+23]), "+f"(d[O+24]), "+f"(d[O+25]), "+f"(d[O+26]), "+f"(d[O+27]), "+f"(d[O+28]), "+f"(d[O+29]), "+f"(d[O+30]), "+f"(d[O+31])
   : "l"(da), "l"(db), "n"(TB));
  else if constexpr (ACC == 0) asm volatile("wgmma.mma_async.sync.aligned.m64n64k16.f32.bf16.bf16 {%0,%1,%2,%3,%4,%5,%6,%7,%8,%9,%10,%11,%12,%13,%14,%15,%16,%17,%18,%19,%20,%21,%22,%23,%24,%25,%26,%27,%28,%29,%30,%31}, %32, %33, 0, 1, 1, 0, %34;"
   : "=f"(d[O+0]), "=f"(d[O+1]), "=f"(d[O+2]), "=f"(d[O+3]), "=f"(d[O+4]), "=f"(d[O+5]), "=f"(d[O+6]), "=f"(d[O+7]), "=f"(d[O+8]), "=f"(d[O+9]), "=f"(d[O+10]), "=f"(d[O+11]), "=f"(d[O+12]), "=f"(d[O+13]), "=f"(d[O+14]), "=f"(d[O+15]), "=f"(d[O+16]), "=f"(d[O+17]), "=f"(d[O+18]), "=f"(d[O+19]), "=f"(d[O+20]), "=f"(d[O+21]), "=f"(d[O+22]), "=f"(d[O+23]), "=f"(d[O+24]), "=f"(d[O+25]), "=f"(d[O+26]), "=f"(d[O+27]), "=f"(d[O+28]), "=f"(d[O+29]), "=f"(d[O+30]), "=f"(d[O+31])
   : "l"(da), "l"(db), "n"(TB));
  else asm volatile("{\n.reg .pred p;\nsetp.ne.b32 p, %35, 0;\nwgmma.mma_async.sync.aligned.m64n64k16.f32.bf16.bf16 {%0,%1,%2,%3,%4,%5,%6,%7,%8,%9,%10,%11,%12,%13,%14,%15,%16,%17,%18,%19,%20,%21,%22,%23,%24,%25,%26,%27,%28,%29,%30,%31}, %32, %33, p, 1, 1, 0, %34;\n}"
   : "+f"(d[O+0]), "+f"(d[O+1]), "+f"(d[O+2]), "+f"(d[O+3]), "+f"(d[O+4]), "+f"(d[O+5]), "+f"(d[O+6]), "+f"(d[O+7]), "+f"(d[O+8]), "+f"(d[O+9]), "+f"(d[O+10]), "+f"(d[O+11]), "+f"(d[O+12]), "+f"(d[O+13]), "+f"(d[O+14]), "+f"(d[O+15]), "+f"(d[O+16]), "+f"(d[O+17]), "+f"(d[O+18]), "+f"(d[O+19]), "+f"(d[O+20]), "+f"(d[O+21]), "+f"(d[O+22]), "+f"(d[O+23]), "+f"(d[O+24]), "+f"(d[O+25]), "+f"(d[O+26]), "+f"(d[O+27]), "+f"(d[O+28]), "+f"(d[O+29]), "+f"(d[O+30]), "+f"(d[O+31])
   : "l"(da), "l"(db), "n"(TB), "r"(sd));
}
template<int O,int TB,int ACC,int NN> __device__ __forceinline__ void mma_rs64(float (&d)[NN], uint32_t a0, uint32_t a1, uint32_t a2, uint32_t a3, uint64_t db, int sd = 0){
  if constexpr (ACC == 1) asm volatile("wgmma.mma_async.sync.aligned.m64n64k16.f32.bf16.bf16 {%0,%1,%2,%3,%4,%5,%6,%7,%8,%9,%10,%11,%12,%13,%14,%15,%16,%17,%18,%19,%20,%21,%22,%23,%24,%25,%26,%27,%28,%29,%30,%31}, {%32,%33,%34,%35}, %36, 1, 1, 1, %37;"
   : "+f"(d[O+0]), "+f"(d[O+1]), "+f"(d[O+2]), "+f"(d[O+3]), "+f"(d[O+4]), "+f"(d[O+5]), "+f"(d[O+6]), "+f"(d[O+7]), "+f"(d[O+8]), "+f"(d[O+9]), "+f"(d[O+10]), "+f"(d[O+11]), "+f"(d[O+12]), "+f"(d[O+13]), "+f"(d[O+14]), "+f"(d[O+15]), "+f"(d[O+16]), "+f"(d[O+17]), "+f"(d[O+18]), "+f"(d[O+19]), "+f"(d[O+20]), "+f"(d[O+21]), "+f"(d[O+22]), "+f"(d[O+23]), "+f"(d[O+24]), "+f"(d[O+25]), "+f"(d[O+26]), "+f"(d[O+27]), "+f"(d[O+28]), "+f"(d[O+29]), "+f"(d[O+30]), "+f"(d[O+31])
   : "r"(a0), "r"(a1), "r"(a2), "r"(a3), "l"(db), "n"(TB));
  else if constexpr (ACC == 0) asm volatile("wgmma.mma_async.sync.aligned.m64n64k16.f32.bf16.bf16 {%0,%1,%2,%3,%4,%5,%6,%7,%8,%9,%10,%11,%12,%13,%14,%15,%16,%17,%18,%19,%20,%21,%22,%23,%24,%25,%26,%27,%28,%29,%30,%31}, {%32,%33,%34,%35}, %36, 0, 1, 1, %37;"
   : "=f"(d[O+0]), "=f"(d[O+1]), "=f"(d[O+2]), "=f"(d[O+3]), "=f"(d[O+4]), "=f"(d[O+5]), "=f"(d[O+6]), "=f"(d[O+7]), "=f"(d[O+8]), "=f"(d[O+9]), "=f"(d[O+10]), "=f"(d[O+11]), "=f"(d[O+12]), "=f"(d[O+13]), "=f"(d[O+14]), "=f"(d[O+15]), "=f"(d[O+16]), "=f"(d[O+17]), "=f"(d[O+18]), "=f"(d[O+19]), "=f"(d[O+20]), "=f"(d[O+21]), "=f"(d[O+22]), "=f"(d[O+23]), "=f"(d[O+24]), "=f"(d[O+25]), "=f"(d[O+26]), "=f"(d[O+27]), "=f"(d[O+28]), "=f"(d[O+29]), "=f"(d[O+30]), "=f"(d[O+31])
   : "r"(a0), "r"(a1), "r"(a2), "r"(a3), "l"(db), "n"(TB));
  else asm volatile("{\n.reg .pred p;\nsetp.ne.b32 p, %38, 0;\nwgmma.mma_async.sync.aligned.m64n64k16.f32.bf16.bf16 {%0,%1,%2,%3,%4,%5,%6,%7,%8,%9,%10,%11,%12,%13,%14,%15,%16,%17,%18,%19,%20,%21,%22,%23,%24,%25,%26,%27,%28,%29,%30,%31}, {%32,%33,%34,%35}, %36, p, 1, 1, %37;\n}"
   : "+f"(d[O+0]), "+f"(d[O+1]), "+f"(d[O+2]), "+f"(d[O+3]), "+f"(d[O+4]), "+f"(d[O+5]), "+f"(d[O+6]), "+f"(d[O+7]), "+f"(d[O+8]), "+f"(d[O+9]), "+f"(d[O+10]), "+f"(d[O+11]), "+f"(d[O+12]), "+f"(d[O+13]), "+f"(d[O+14]), "+f"(d[O+15]), "+f"(d[O+16]), "+f"(d[O+17]), "+f"(d[O+18]), "+f"(d[O+19]), "+f"(d[O+20]), "+f"(d[O+21]), "+f"(d[O+22]), "+f"(d[O+23]), "+f"(d[O+24]), "+f"(d[O+25]), "+f"(d[O+26]), "+f"(d[O+27]), "+f"(d[O+28]), "+f"(d[O+29]), "+f"(d[O+30]), "+f"(d[O+31])
   : "r"(a0), "r"(a1), "r"(a2), "r"(a3), "l"(db), "n"(TB), "r"(sd));
}
template<int O,int TB,int ACC,int NN> __device__ __forceinline__ void mma_ss128(float (&d)[NN], uint64_t da, uint64_t db, int sd = 0){
  if constexpr (ACC == 1) asm volatile("wgmma.mma_async.sync.aligned.m64n128k16.f32.bf16.bf16 {%0,%1,%2,%3,%4,%5,%6,%7,%8,%9,%10,%11,%12,%13,%14,%15,%16,%17,%18,%19,%20,%21,%22,%23,%24,%25,%26,%27,%28,%29,%30,%31,%32,%33,%34,%35,%36,%37,%38,%39,%40,%41,%42,%43,%44,%45,%46,%47,%48,%49,%50,%51,%52,%53,%54,%55,%56,%57,%58,%59,%60,%61,%62,%63}, %64, %65, 1, 1, 1, 0, %66;"
   : "+f"(d[O+0]), "+f"(d[O+1]), "+f"(d[O+2]), "+f"(d[O+3]), "+f"(d[O+4]), "+f"(d[O+5]), "+f"(d[O+6]), "+f"(d[O+7]), "+f"(d[O+8]), "+f"(d[O+9]), "+f"(d[O+10]), "+f"(d[O+11]), "+f"(d[O+12]), "+f"(d[O+13]), "+f"(d[O+14]), "+f"(d[O+15]), "+f"(d[O+16]), "+f"(d[O+17]), "+f"(d[O+18]), "+f"(d[O+19]), "+f"(d[O+20]), "+f"(d[O+21]), "+f"(d[O+22]), "+f"(d[O+23]), "+f"(d[O+24]), "+f"(d[O+25]), "+f"(d[O+26]), "+f"(d[O+27]), "+f"(d[O+28]), "+f"(d[O+29]), "+f"(d[O+30]), "+f"(d[O+31]), "+f"(d[O+32]), "+f"(d[O+33]), "+f"(d[O+34]), "+f"(d[O+35]), "+f"(d[O+36]), "+f"(d[O+37]), "+f"(d[O+38]), "+f"(d[O+39]), "+f"(d[O+40]), "+f"(d[O+41]), "+f"(d[O+42]), "+f"(d[O+43]), "+f"(d[O+44]), "+f"(d[O+45]), "+f"(d[O+46]), "+f"(d[O+47]), "+f"(d[O+48]), "+f"(d[O+49]), "+f"(d[O+50]), "+f"(d[O+51]), "+f"(d[O+52]), "+f"(d[O+53]), "+f"(d[O+54]), "+f"(d[O+55]), "+f"(d[O+56]), "+f"(d[O+57]), "+f"(d[O+58]), "+f"(d[O+59]), "+f"(d[O+60]), "+f"(d[O+61]), "+f"(d[O+62]), "+f"(d[O+63])
   : "l"(da), "l"(db), "n"(TB));
  else if constexpr (ACC == 0) asm volatile("wgmma.mma_async.sync.aligned.m64n128k16.f32.bf16.bf16 {%0,%1,%2,%3,%4,%5,%6,%7,%8,%9,%10,%11,%12,%13,%14,%15,%16,%17,%18,%19,%20,%21,%22,%23,%24,%25,%26,%27,%28,%29,%30,%31,%32,%33,%34,%35,%36,%37,%38,%39,%40,%41,%42,%43,%44,%45,%46,%47,%48,%49,%50,%51,%52,%53,%54,%55,%56,%57,%58,%59,%60,%61,%62,%63}, %64, %65, 0, 1, 1, 0, %66;"
   : "=f"(d[O+0]), "=f"(d[O+1]), "=f"(d[O+2]), "=f"(d[O+3]), "=f"(d[O+4]), "=f"(d[O+5]), "=f"(d[O+6]), "=f"(d[O+7]), "=f"(d[O+8]), "=f"(d[O+9]), "=f"(d[O+10]), "=f"(d[O+11]), "=f"(d[O+12]), "=f"(d[O+13]), "=f"(d[O+14]), "=f"(d[O+15]), "=f"(d[O+16]), "=f"(d[O+17]), "=f"(d[O+18]), "=f"(d[O+19]), "=f"(d[O+20]), "=f"(d[O+21]), "=f"(d[O+22]), "=f"(d[O+23]), "=f"(d[O+24]), "=f"(d[O+25]), "=f"(d[O+26]), "=f"(d[O+27]), "=f"(d[O+28]), "=f"(d[O+29]), "=f"(d[O+30]), "=f"(d[O+31]), "=f"(d[O+32]), "=f"(d[O+33]), "=f"(d[O+34]), "=f"(d[O+35]), "=f"(d[O+36]), "=f"(d[O+37]), "=f"(d[O+38]), "=f"(d[O+39]), "=f"(d[O+40]), "=f"(d[O+41]), "=f"(d[O+42]), "=f"(d[O+43]), "=f"(d[O+44]), "=f"(d[O+45]), "=f"(d[O+46]), "=f"(d[O+47]), "=f"(d[O+48]), "=f"(d[O+49]), "=f"(d[O+50]), "=f"(d[O+51]), "=f"(d[O+52]), "=f"(d[O+53]), "=f"(d[O+54]), "=f"(d[O+55]), "=f"(d[O+56]), "=f"(d[O+57]), "=f"(d[O+58]), "=f"(d[O+59]), "=f"(d[O+60]), "=f"(d[O+61]), "=f"(d[O+62]), "=f"(d[O+63])
   : "l"(da), "l"(db), "n"(TB));
  else asm volatile("{\n.reg .pred p;\nsetp.ne.b32 p, %67, 0;\nwgmma.mma_async.sync.aligned.m64n128k16.f32.bf16.bf16 {%0,%1,%2,%3,%4,%5,%6,%7,%8,%9,%10,%11,%12,%13,%14,%15,%16,%17,%18,%19,%20,%21,%22,%23,%24,%25,%26,%27,%28,%29,%30,%31,%32,%33,%34,%35,%36,%37,%38,%39,%40,%41,%42,%43,%44,%45,%46,%47,%48,%49,%50,%51,%52,%53,%54,%55,%56,%57,%58,%59,%60,%61,%62,%63}, %64, %65, p, 1, 1, 0, %66;\n}"
   : "+f"(d[O+0]), "+f"(d[O+1]), "+f"(d[O+2]), "+f"(d[O+3]), "+f"(d[O+4]), "+f"(d[O+5]), "+f"(d[O+6]), "+f"(d[O+7]), "+f"(d[O+8]), "+f"(d[O+9]), "+f"(d[O+10]), "+f"(d[O+11]), "+f"(d[O+12]), "+f"(d[O+13]), "+f"(d[O+14]), "+f"(d[O+15]), "+f"(d[O+16]), "+f"(d[O+17]), "+f"(d[O+18]), "+f"(d[O+19]), "+f"(d[O+20]), "+f"(d[O+21]), "+f"(d[O+22]), "+f"(d[O+23]), "+f"(d[O+24]), "+f"(d[O+25]), "+f"(d[O+26]), "+f"(d[O+27]), "+f"(d[O+28]), "+f"(d[O+29]), "+f"(d[O+30]), "+f"(d[O+31]), "+f"(d[O+32]), "+f"(d[O+33]), "+f"(d[O+34]), "+f"(d[O+35]), "+f"(d[O+36]), "+f"(d[O+37]), "+f"(d[O+38]), "+f"(d[O+39]), "+f"(d[O+40]), "+f"(d[O+41]), "+f"(d[O+42]), "+f"(d[O+43]), "+f"(d[O+44]), "+f"(d[O+45]), "+f"(d[O+46]), "+f"(d[O+47]), "+f"(d[O+48]), "+f"(d[O+49]), "+f"(d[O+50]), "+f"(d[O+51]), "+f"(d[O+52]), "+f"(d[O+53]), "+f"(d[O+54]), "+f"(d[O+55]), "+f"(d[O+56]), "+f"(d[O+57]), "+f"(d[O+58]), "+f"(d[O+59]), "+f"(d[O+60]), "+f"(d[O+61]), "+f"(d[O+62]), "+f"(d[O+63])
   : "l"(da), "l"(db), "n"(TB), "r"(sd));
}
template<int O,int TB,int ACC,int NN> __device__ __forceinline__ void mma_rs128(float (&d)[NN], uint32_t a0, uint32_t a1, uint32_t a2, uint32_t a3, uint64_t db, int sd = 0){
  if constexpr (ACC == 1) asm volatile("wgmma.mma_async.sync.aligned.m64n128k16.f32.bf16.bf16 {%0,%1,%2,%3,%4,%5,%6,%7,%8,%9,%10,%11,%12,%13,%14,%15,%16,%17,%18,%19,%20,%21,%22,%23,%24,%25,%26,%27,%28,%29,%30,%31,%32,%33,%34,%35,%36,%37,%38,%39,%40,%41,%42,%43,%44,%45,%46,%47,%48,%49,%50,%51,%52,%53,%54,%55,%56,%57,%58,%59,%60,%61,%62,%63}, {%64,%65,%66,%67}, %68, 1, 1, 1, %69;"
   : "+f"(d[O+0]), "+f"(d[O+1]), "+f"(d[O+2]), "+f"(d[O+3]), "+f"(d[O+4]), "+f"(d[O+5]), "+f"(d[O+6]), "+f"(d[O+7]), "+f"(d[O+8]), "+f"(d[O+9]), "+f"(d[O+10]), "+f"(d[O+11]), "+f"(d[O+12]), "+f"(d[O+13]), "+f"(d[O+14]), "+f"(d[O+15]), "+f"(d[O+16]), "+f"(d[O+17]), "+f"(d[O+18]), "+f"(d[O+19]), "+f"(d[O+20]), "+f"(d[O+21]), "+f"(d[O+22]), "+f"(d[O+23]), "+f"(d[O+24]), "+f"(d[O+25]), "+f"(d[O+26]), "+f"(d[O+27]), "+f"(d[O+28]), "+f"(d[O+29]), "+f"(d[O+30]), "+f"(d[O+31]), "+f"(d[O+32]), "+f"(d[O+33]), "+f"(d[O+34]), "+f"(d[O+35]), "+f"(d[O+36]), "+f"(d[O+37]), "+f"(d[O+38]), "+f"(d[O+39]), "+f"(d[O+40]), "+f"(d[O+41]), "+f"(d[O+42]), "+f"(d[O+43]), "+f"(d[O+44]), "+f"(d[O+45]), "+f"(d[O+46]), "+f"(d[O+47]), "+f"(d[O+48]), "+f"(d[O+49]), "+f"(d[O+50]), "+f"(d[O+51]), "+f"(d[O+52]), "+f"(d[O+53]), "+f"(d[O+54]), "+f"(d[O+55]), "+f"(d[O+56]), "+f"(d[O+57]), "+f"(d[O+58]), "+f"(d[O+59]), "+f"(d[O+60]), "+f"(d[O+61]), "+f"(d[O+62]), "+f"(d[O+63])
   : "r"(a0), "r"(a1), "r"(a2), "r"(a3), "l"(db), "n"(TB));
  else if constexpr (ACC == 0) asm volatile("wgmma.mma_async.sync.aligned.m64n128k16.f32.bf16.bf16 {%0,%1,%2,%3,%4,%5,%6,%7,%8,%9,%10,%11,%12,%13,%14,%15,%16,%17,%18,%19,%20,%21,%22,%23,%24,%25,%26,%27,%28,%29,%30,%31,%32,%33,%34,%35,%36,%37,%38,%39,%40,%41,%42,%43,%44,%45,%46,%47,%48,%49,%50,%51,%52,%53,%54,%55,%56,%57,%58,%59,%60,%61,%62,%63}, {%64,%65,%66,%67}, %68, 0, 1, 1, %69;"
   : "=f"(d[O+0]), "=f"(d[O+1]), "=f"(d[O+2]), "=f"(d[O+3]), "=f"(d[O+4]), "=f"(d[O+5]), "=f"(d[O+6]), "=f"(d[O+7]), "=f"(d[O+8]), "=f"(d[O+9]), "=f"(d[O+10]), "=f"(d[O+11]), "=f"(d[O+12]), "=f"(d[O+13]), "=f"(d[O+14]), "=f"(d[O+15]), "=f"(d[O+16]), "=f"(d[O+17]), "=f"(d[O+18]), "=f"(d[O+19]), "=f"(d[O+20]), "=f"(d[O+21]), "=f"(d[O+22]), "=f"(d[O+23]), "=f"(d[O+24]), "=f"(d[O+25]), "=f"(d[O+26]), "=f"(d[O+27]), "=f"(d[O+28]), "=f"(d[O+29]), "=f"(d[O+30]), "=f"(d[O+31]), "=f"(d[O+32]), "=f"(d[O+33]), "=f"(d[O+34]), "=f"(d[O+35]), "=f"(d[O+36]), "=f"(d[O+37]), "=f"(d[O+38]), "=f"(d[O+39]), "=f"(d[O+40]), "=f"(d[O+41]), "=f"(d[O+42]), "=f"(d[O+43]), "=f"(d[O+44]), "=f"(d[O+45]), "=f"(d[O+46]), "=f"(d[O+47]), "=f"(d[O+48]), "=f"(d[O+49]), "=f"(d[O+50]), "=f"(d[O+51]), "=f"(d[O+52]), "=f"(d[O+53]), "=f"(d[O+54]), "=f"(d[O+55]), "=f"(d[O+56]), "=f"(d[O+57]), "=f"(d[O+58]), "=f"(d[O+59]), "=f"(d[O+60]), "=f"(d[O+61]), "=f"(d[O+62]), "=f"(d[O+63])
   : "r"(a0), "r"(a1), "r"(a2), "r"(a3), "l"(db), "n"(TB));
  else asm volatile("{\n.reg .pred p;\nsetp.ne.b32 p, %70, 0;\nwgmma.mma_async.sync.aligned.m64n128k16.f32.bf16.bf16 {%0,%1,%2,%3,%4,%5,%6,%7,%8,%9,%10,%11,%12,%13,%14,%15,%16,%17,%18,%19,%20,%21,%22,%23,%24,%25,%26,%27,%28,%29,%30,%31,%32,%33,%34,%35,%36,%37,%38,%39,%40,%41,%42,%43,%44,%45,%46,%47,%48,%49,%50,%51,%52,%53,%54,%55,%56,%57,%58,%59,%60,%61,%62,%63}, {%64,%65,%66,%67}, %68, p, 1, 1, %69;\n}"
   : "+f"(d[O+0]), "+f"(d[O+1]), "+f"(d[O+2]), "+f"(d[O+3]), "+f"(d[O+4]), "+f"(d[O+5]), "+f"(d[O+6]), "+f"(d[O+7]), "+f"(d[O+8]), "+f"(d[O+9]), "+f"(d[O+10]), "+f"(d[O+11]), "+f"(d[O+12]), "+f"(d[O+13]), "+f"(d[O+14]), "+f"(d[O+15]), "+f"(d[O+16]), "+f"(d[O+17]), "+f"(d[O+18]), "+f"(d[O+19]), "+f"(d[O+20]), "+f"(d[O+21]), "+f"(d[O+22]), "+f"(d[O+23]), "+f"(d[O+24]), "+f"(d[O+25]), "+f"(d[O+26]), "+f"(d[O+27]), "+f"(d[O+28]), "+f"(d[O+29]), "+f"(d[O+30]), "+f"(d[O+31]), "+f"(d[O+32]), "+f"(d[O+33]), "+f"(d[O+34]), "+f"(d[O+35]), "+f"(d[O+36]), "+f"(d[O+37]), "+f"(d[O+38]), "+f"(d[O+39]), "+f"(d[O+40]), "+f"(d[O+41]), "+f"(d[O+42]), "+f"(d[O+43]), "+f"(d[O+44]), "+f"(d[O+45]), "+f"(d[O+46]), "+f"(d[O+47]), "+f"(d[O+48]), "+f"(d[O+49]), "+f"(d[O+50]), "+f"(d[O+51]), "+f"(d[O+52]), "+f"(d[O+53]), "+f"(d[O+54]), "+f"(d[O+55]), "+f"(d[O+56]), "+f"(d[O+57]), "+f"(d[O+58]), "+f"(d[O+59]), "+f"(d[O+60]), "+f"(d[O+61]), "+f"(d[O+62]), "+f"(d[O+63])
   : "r"(a0), "r"(a1), "r"(a2), "r"(a3), "l"(db), "n"(TB), "r"(sd));
}

__host__ __device__ constexpr int brev(int a, int bits) { int r = 0; for (int i = 0; i < bits; i++) r |= ((a >> i) & 1) << (bits - 1 - i); return r; }
__host__ __device__ constexpr int ilog2(int n) { return n <= 1 ? 0 : 1 + ilog2(n / 2); }
template <int SG, int A> __device__ __forceinline__ void bfly(float2& a, float2& b) {
  if constexpr (A == 0) {
    float tr = a.x - b.x, ti = a.y - b.y; a.x += b.x; a.y += b.y; b.x = tr; b.y = ti;
  } else if constexpr (A == 8) {
    float pr = SG > 0 ? -b.y : b.y, pi = SG > 0 ? b.x : -b.x;
    b.x = a.x - pr; b.y = a.y - pi; a.x += pr; a.y += pi;
  } else {
    constexpr float wr = tbl::W32<A>::c, wi = SG * tbl::W32<A>::s;
    float tr = fmaf(wr, b.x, a.x), ti = fmaf(wr, b.y, a.y);
    tr = fmaf(-wi, b.y, tr); ti = fmaf(wi, b.x, ti);
    b.x = fmaf(2.f, a.x, -tr); b.y = fmaf(2.f, a.y, -ti); a.x = tr; a.y = ti;
  }
}
template <int SG, int N, int O, int ST, int A> __device__ __forceinline__ void dft_comb(float2 (&x)[32]) {
  if constexpr (A < N / 2) {
    constexpr int p = O + 2 * ST * brev(A, ilog2(N / 2));
    bfly<SG, A * (32 / N)>(x[p], x[p + ST]);
    dft_comb<SG, N, O, ST, A + 1>(x);
  }
}
template <int SG, int N, int O, int ST> __device__ __forceinline__ void dft(float2 (&x)[32]) {
  if constexpr (N > 1) {
    dft<SG, N / 2, O, 2 * ST>(x);
    dft<SG, N / 2, O + ST, 2 * ST>(x);
    dft_comb<SG, N, O, ST, 0>(x);
  }
}

#define XFIRST 5
#define WPACE 100
#define TPACE 40
#define PFMODE 0
#define MAPMODE 0
template <int V> struct IC { static constexpr int value = V; };
struct Maps { CUtensorMap ft, g32, x, u32, g64, u64, e, wr, wi, d192, d32, fg; };

constexpr int NCTA = 132;
constexpr int U = 16384;
constexpr int TB = 36864;
constexpr int NR = 5;
constexpr int OFF_RING = 8 * U, OFF_Z = 9 * U, OFF_T = 13 * U;
constexpr int OFF_BAR = 14 * U;
constexpr int SMEM_BYTES = OFF_BAR + 512;
constexpr int B_FX = 0, B_FA = 8, B_FT = 13, B_Z = 17, B_W = 21, B_HX = 22, B_HT = 23, B_HP = 24;
constexpr int B_EA = 27, B_ET = 32, B_RDY = 36;
constexpr int B_T = 37, NBAR = 38;
__host__ __device__ constexpr int rslot(int n) { return (n + 2) % NR; }
__host__ __device__ constexpr int rpar(int n) { return (n / NR) & 1; }

__global__ void __cluster_dims__(2, 1, 1) __launch_bounds__(512, 1)
fused_kernel(const __grid_constant__ Maps maps, const __nv_bfloat16* __restrict__ x, const __nv_bfloat16* __restrict__ w_r,
             const __nv_bfloat16* __restrict__ w_i, const __nv_bfloat16* __restrict__ gate_w, const __nv_bfloat16* __restrict__ Wd,
             __nv_bfloat16* __restrict__ out) {
  extern __shared__ __align__(1024) uint8_t smem[];
  const uint32_t sb = smem_u32(smem);
  const uint32_t bars = sb + OFF_BAR;
  const int tid = threadIdx.x, lane = tid & 31;
  const int warp = __shfl_sync(0xffffffffu, tid >> 5, 0);
  const bool helper = blockIdx.x >= 128;
  const int cl = (blockIdx.x >> 1) & 63, rank = blockIdx.x & 1;
  const int q4 = cl & 3, rb = cl >> 2;
  const int j = 2 * q4 + rank;
  const int f_full = 448 * q4 + (rank ? 256 : 0);
  const int f_half = 448 * q4 + (rank ? 224 : 192);
  const int kg = 2 * j + (rb >> 3), tn = rb & 7;

  if (tid == 64) { PROF_EV(0); PROF_CK(40); }
  auto ring_part = [&](int p, int n, int slot) {
    const uint32_t fb = bars + 8 * (B_FA + slot), dst = sb + OFF_RING + slot * U;
    const bool table = n == 9 || n == 10 || n >= 34;
    const int q = n == 8 ? 0 : n - 10;
    if (p == 0) {
      mbar_expect_tx(fb, U);
      if (n < 8) tma2d(dst, &maps.ft, fb, 64 * n, 64 * j);
      else if (table) tma4d(dst, &maps.e, fb, 0, 0, 0, 2 * rb + (n >= 34 ? n - 34 : n - 9));
      else tma2d(dst, &maps.g64, fb, f_full + 64 * (q >> 3), 64 * (q & 7));
    } else if (p == 1) {
      if (n < 8) { tma2d(dst + 8192, &maps.g32, fb, f_half, 64 * n); tma2d(dst + 12288, &maps.u32, fb, f_half, 64 * n); }
      else if (!table) tma2d(dst + 8192, &maps.u64, fb, f_full + 64 * (q >> 3), 64 * (q & 7));
    }
  };
  auto x_load = [&](int q) {
    mbar_expect_tx(bars + 8 * (B_FX + q), U);
    tma3d(sb + q * U, &maps.x, bars + 8 * (B_FX + q), 64 * q, 0, 2 * rb);
  };
  if (warp >= 12) {
    if (lane == 0) asm volatile("prefetch.tensormap [%0];" ::"l"((const char*)&maps + (warp - 12) * 128) : "memory");
    if (warp == 15) {
      if (lane == 0) {
#pragma unroll
        for (int i = B_FT; i < NBAR; i++) mbar_init(bars + 8 * i, i < B_EA ? 1 : i < B_T ? 2 : 4);
#pragma unroll
        for (int i = 0; i < 4; i++) mbar_expect_tx(bars + 8 * (B_Z + i), U);
        asm volatile("fence.mbarrier_init.release.cluster;" ::: "memory");
#pragma unroll
        for (int i = 4; i < 12; i++) asm volatile("prefetch.tensormap [%0];" ::"l"((const char*)&maps + i * 128) : "memory");
      }
    } else if (warp == 14) {
      if (lane == 0) {
#pragma unroll
        for (int i = 0; i < 8; i++) mbar_init(bars + 8 * (B_FX + i), 1);
        asm volatile("fence.proxy.async.shared::cta;" ::: "memory");
        if (!helper) x_load(0);
      }
    } else {
      if (warp == 12 && lane == 0) {
#pragma unroll
        for (int i = 0; i < NR; i++) mbar_init(bars + 8 * (B_FA + i), 1);
        asm volatile("fence.proxy.async.shared::cta;" ::: "memory");
      }
      asm volatile("bar.sync 2, 64;" ::: "memory");
      if (lane == 0 && !helper) ring_part(warp - 12, 0, rslot(0));
    }
    __syncwarp();
    asm volatile("bar.arrive 0, 512;" ::: "memory");
  } else {
    asm volatile("bar.sync 0, 512;" ::: "memory");
  }
  asm volatile("barrier.cluster.arrive.relaxed.aligned;" ::: "memory");
  if (tid == 64) PROF_EV(38);

  if (warp >= 12) {
    asm volatile("setmaxnreg.dec.sync.aligned.u32 24;");
    if (warp < 14) {
      if (lane == 0 && !helper) {
#pragma unroll 1
        for (int n = 1; n < NR; n++) ring_part(warp - 12, n, rslot(n));
      }
    } else if (warp == 14) {
      if (lane == 0 && !helper) {
#pragma unroll 1
        for (int q = 1; q < XFIRST; q++) x_load(q);
      }
    }
    asm volatile("bar.sync 3, 128;" ::: "memory");
    if (lane == 0 && !helper) {
      if (warp < 14) {
        int slot = rslot(NR), par = 0;
#pragma unroll 1
        for (int n = NR; n < 36; n++) {
          mbar_wait(bars + 8 * (B_EA + slot), par);
          ring_part(warp - 12, n, slot);
          if (++slot == NR) slot = 0;
          if (slot == rslot(0)) par ^= 1;
        }
      } else if (warp == 15) {
        const unsigned ep1 = ld_x1(&g_epoch[blockIdx.x * 8]) + 1;
        hint_wait(&g_cntX[32 * j], ep1 * 128u); mbar_arrive(bars + 8 * B_HX);
        hint_wait(&g_cntT[32 * j], ep1 * (j == 0 ? 68u : 64u)); mbar_arrive(bars + 8 * B_HT);
#pragma unroll 1
        for (int i = 0; i < 3; i++) { hint_wait(&g_cntP[32 * (rb * 8 + j) + i], ep1 * 8u); mbar_arrive(bars + 8 * (B_HP + i)); }
      } else {
#pragma unroll 1
        for (int q = XFIRST; q < 8; q++) { mbar_wait(bars + 8 * (B_FX + q - XFIRST), 0); x_load(q); }
        PROF_EV(31);
#pragma unroll 1
        for (int t = 0; t < 8; t++) {
          const int i = t < 3 ? t + 1 : t < 6 ? t - 2 : 0;
          const int col = 64 * (2 * ((q4 + i) & 3) + ((t < 3 || t == 6) ? 1 - rank : rank));
          const uint32_t fb = bars + 8 * (B_FT + (t & 3)), dst = sb + (t & 3) * TB;
          mbar_wait(bars + 8 * (B_ET + (t & 3)), t >> 2);
          mbar_expect_tx(fb, TB);
          tma2d(dst, &maps.d192, fb, col, f_full);
          tma2d(dst + 24576, &maps.d32, fb, col, f_half);
          tma4d(dst + 28672, &maps.fg, fb, col, 0, 0, 4 * j);
        }
      }
    }
  } else if (warp >= 8) {
    asm volatile("setmaxnreg.dec.sync.aligned.u32 88;");
    const int t = tid - 256, w = warp - 8;
    const float scale = 2.0f / (2048.0f * 512.0f);
    const uint32_t ep = ld_x1(&g_epoch[blockIdx.x * 8]);
    if (!helper) {
      uint4 xv[8], gv[2];
#pragma unroll
      for (int i = 0; i < 4; i++) {
        const int r = 16 * j + 4 * w + i;
        const uint4* p = (const uint4*)(x + (size_t)(2 * rb + (r >> 6) + 32 * (r & 63)) * 512) + lane;
        xv[2 * i] = __ldg(p); xv[2 * i + 1] = __ldg(p + 32);
      }
      gv[0] = __ldg((const uint4*)gate_w + lane); gv[1] = __ldg((const uint4*)gate_w + lane + 32);
      const uint32_t tag = (ep + 1) & 1;
      {
        float z[4];
#pragma unroll
        for (int i = 0; i < 4; i++) {
          float a = 0.f;
#pragma unroll
          for (int hh = 0; hh < 2; hh++) {
            const uint4 u = xv[2 * i + hh], v = gv[hh];
            a = fmaf(bf_lo(u.x), bf_lo(v.x), a); a = fmaf(bf_hi(u.x), bf_hi(v.x), a);
            a = fmaf(bf_lo(u.y), bf_lo(v.y), a); a = fmaf(bf_hi(u.y), bf_hi(v.y), a);
            a = fmaf(bf_lo(u.z), bf_lo(v.z), a); a = fmaf(bf_hi(u.z), bf_hi(v.z), a);
            a = fmaf(bf_lo(u.w), bf_lo(v.w), a); a = fmaf(bf_hi(u.w), bf_hi(v.w), a);
          }
#pragma unroll
          for (int o = 16; o; o >>= 1) a += __shfl_xor_sync(0xffffffffu, a, o);
          z[i] = a;
        }
        if (lane < 4) {
          const float zz = lane == 0 ? z[0] : lane == 1 ? z[1] : lane == 2 ? z[2] : z[3];
          asm volatile("st.relaxed.gpu.global.f32 [%0], %1;" ::"l"(g_gate + rb * 128 + 16 * j + 4 * w + lane), "f"(tagf(1.0f / (1.0f + __expf(-zz)), tag)) : "memory");
        }
        if (t == 0) PROF_EV(18);
      }
      if (w == 0) {
        const int c = lane >> 4, jj = 16 * blockIdx.x + (lane & 15), jm = (2048 - jj) & 2047;
        const unsigned short* pr = (const unsigned short*)w_r + 256 * c;
        const unsigned short* pi = (const unsigned short*)w_i + 256 * c;
        const float wr = 0.5f * (bf_lo(__ldg(pr + jj * 257)) + bf_lo(__ldg(pr + jm * 257)));
        const float wi = 0.5f * (bf_lo(__ldg(pi + jj * 257)) - bf_lo(__ldg(pi + jm * 257)));
        st_x2(g_Wh + c * 2048 + jj, tagf(c ? -wi : wr, tag), c ? wr : wi);
        __syncwarp();
        if (lane == 0) hint_add(&g_cntW[0]);
      }
      const int k = 16 * kg + (t & 15), j1 = 8 * tn + (t >> 4);
      {
        const unsigned short* p = (const unsigned short*)(smem + OFF_T) + (t >> 4) * 25 + (t & 15);
        uint32_t wv[32];
        auto w_load = [&](const CUtensorMap* m) {
          mbar_expect_tx(bars + 8 * B_W, 12288);
#pragma unroll 1
          for (int i = 0; i < 4; i++) { tma4d(sb + OFF_T + i * 3072, m, bars + 8 * B_W, 16 * kg, 0, tn, 8 * i); __nanosleep(WPACE); }
        };
        if (t == 0) { mbar_wait(bars + 8 * (B_FX + 7), 0); PROF_EV(32); w_load(&maps.wr); }
        mbar_wait(bars + 8 * B_W, 0);
#pragma unroll
        for (int a = 0; a < 32; a++) wv[a] = p[a * 192];
        asm volatile("bar.sync 1, 128;" ::: "memory");
        if (t == 0) w_load(&maps.wi);
        mbar_wait(bars + 8 * B_W, 1);
#pragma unroll
        for (int a = 0; a < 32; a++) wv[a] |= (uint32_t)p[a * 192] << 16;
        asm volatile("bar.sync 1, 128;" ::: "memory");
#pragma unroll
        for (int a = 0; a < 8; a++) *(uint4*)(smem + OFF_T + (a * 128 + t) * 16) = make_uint4(wv[4 * a], wv[4 * a + 1], wv[4 * a + 2], wv[4 * a + 3]);
      }
      if (t == 0) PROF_EV(11);
      mbar_wait(bars + 8 * B_HX, 0);
      float2 v[32];
      if (t == 0) PROF_EV(22);
      {
        const uint32_t* src = (const uint32_t*)(g_X1p + (size_t)(kg * 8 + tn) * 2048 + ((t >> 3) & 1) * 32 + w * 8 + (t & 7)) + ((t >> 4) & 1);
        const uint32_t chk = (t & 16) ? 0u : 1u;
        uint32_t u[32];
        const uint32_t t0 = (uint32_t)clock();
        for (;;) {
          uint32_t bad = 0;
#pragma unroll
          for (int a = 0; a < 32; a++) u[a] = ld_x1(src + a * 128);
#pragma unroll
          for (int a = 0; a < 32; a++) bad |= u[a] ^ tag;
          if (!__any_sync(0xffffffffu, bad & chk)) break;
          spin_guard(t0);
        }
#pragma unroll
        for (int a = 0; a < 32; a++) v[a] = make_float2(bf_lo(u[a] & ~chk), bf_hi(u[a]));
      }
      if (t == 0) PROF_EV(12);
      dft<-1, 32, 0, 1>(v);
      float2 y[32];
#pragma unroll
      for (int a4 = 0; a4 < 8; a4++) {
        const uint4 ww = *(const uint4*)(smem + OFF_T + (a4 * 128 + t) * 16);
        const uint32_t wq[4] = {ww.x, ww.y, ww.z, ww.w};
#pragma unroll
        for (int e = 0; e < 4; e++) {
          const float2 z = v[brev(4 * a4 + e, 5)];
          const float wr = bf_lo(wq[e]), wi = bf_hi(wq[e]);
          y[4 * a4 + e] = make_float2(fmaf(z.x, wr, -z.y * wi), fmaf(z.x, wi, z.y * wr));
        }
      }
      dft<1, 32, 0, 1>(y);
      if (t == 0) PROF_EV(16);
      {
        uint2* dst = g_T + (size_t)j * 32768 + (kg & 1) * 1024 + j1 * 16 + (t & 15);
#pragma unroll
        for (int a = 0; a < 16; a++) {
          const float2 u0 = y[brev(2 * a, 5)], u1 = y[brev(2 * a + 1, 5)];
          if (k != 0) st_u2(dst + a * 2048, (pack_bf16(u0.x * scale, u0.y * scale) & ~1u) | tag, pack_bf16(u1.x * scale, u1.y * scale));
          if (TPACE && (a & 3) == 3 && a < 15) __nanosleep(TPACE);
        }
        __syncwarp();
        if (lane == 0) hint_add(&g_cntT[32 * j]);
      }
      if (t == 0) PROF_EV(17);
      {
        const uint4* src = (const uint4*)(g_T + (size_t)(j * 16 + rb) * 2048) + t;
        uint4 u[8];
        mbar_wait(bars + 8 * B_HT, 0);
        if (t == 0) PROF_EV(23);
        const uint32_t t0 = (uint32_t)clock();
        for (;;) {
          uint32_t bad = 0;
#pragma unroll
          for (int a = 0; a < 8; a++) u[a] = ld_x4(src + a * 128);
#pragma unroll
          for (int a = 0; a < 8; a++) bad |= (u[a].x ^ tag) | (u[a].z ^ tag);
          if (!__any_sync(0xffffffffu, bad & 1)) break;
          spin_guard(t0);
        }
        const int r = t >> 3, c = t & 7;
#pragma unroll
        for (int a = 0; a < 8; a++) {
          const uint32_t dst = sb + OFF_T + (16 * (a & 3) + r) * 128 + ((((a >> 2) * 4 + (c >> 1)) ^ (r & 7)) << 4) + (c & 1) * 8;
          asm volatile("st.shared.v2.u32 [%0], {%1,%2};" ::"r"(dst), "r"(u[a].x & ~1u), "r"(u[a].z & ~1u) : "memory");
          asm volatile("st.shared.v2.u32 [%0], {%1,%2};" ::"r"(dst + 8192), "r"(u[a].y), "r"(u[a].w) : "memory");
        }
        asm volatile("fence.proxy.async.shared::cta;" ::: "memory");
        __syncwarp();
        if (lane == 0) mbar_arrive(bars + 8 * B_T);
        if (t == 0) PROF_EV(13);
      }
    } else if (w == 0) {
      const uint32_t tag = (ep + 1) & 1;
      const int c = lane >> 4, j1 = 16 * (blockIdx.x - 128) + (lane & 15);
      float2* wf = (float2*)smem;
      float2 v[32];
      hint_wait(&g_cntW[0], (ep + 1) * 128u);
      load32_tagged(v, g_Wh + c * 2048 + j1, 64, tag);
#pragma unroll
      for (int a = 0; a < 32; a++) wf[a * 32 + lane] = v[a];
      if (t == 0) PROF_EV(11);
      hint_wait(&g_cntX[0], (ep + 1) * 128u);
      load32_tagged(v, g_X1s + c * 2048 + j1, 64, tag);
      if (t == 0) PROF_EV(12);
      dft<-1, 32, 0, 1>(v);
      float2 y[32];
#pragma unroll
      for (int a = 0; a < 32; a++) {
        const float2 z = v[brev(a, 5)], wv = wf[a * 32 + lane];
        y[a] = make_float2(fmaf(z.x, wv.x, -z.y * wv.y), fmaf(z.x, wv.y, z.y * wv.x));
      }
      dft<1, 32, 0, 1>(y);
      if (t == 0) PROF_EV(16);
#pragma unroll
      for (int a = 0; a < 8; a++) {
        uint32_t pk[2];
#pragma unroll
        for (int e = 0; e < 2; e++) {
          const float2 u0 = y[brev(4 * a + e, 5)], u1 = y[brev(4 * a + 2 + e, 5)];
          const float2 keep = c ? u1 : u0, give = c ? u0 : u1;
          const float ox = __shfl_xor_sync(0xffffffffu, give.x, 16), oy = __shfl_xor_sync(0xffffffffu, give.y, 16);
          pk[e] = pack_bf16((keep.x + ox) * (0.5f * scale), (keep.y + oy) * (0.5f * scale));
        }
        st_u2(g_T + (2 * a + c) * 2048 + j1 * 16, (pk[0] & ~1u) | tag, pk[1]);
      }
      __syncwarp();
      if (t == 0) { hint_add(&g_cntT[0]); g_epoch[blockIdx.x * 8] = ep + 1; PROF_EV(13); }
    }
  } else {
    asm volatile("setmaxnreg.inc.sync.aligned.u32 200;");
    if (!helper) {
      const int wg = warp >> 2, w = warp & 3, g = lane >> 2, q = lane & 3;
      const bool elect = (tid & 127) == 0;
      const uint32_t ep = ld_x1(&g_epoch[blockIdx.x * 8]);
      float c1[64], cA[64], c2[64], ci[64], ct[64];
      const int zero = blockIdx.x >> 16;
      uint32_t h[56], yf[16];
      const uint32_t d0 = (sb & 0x3FFFF) >> 4;
      const uint32_t dK = d0 | (1u << 16), dN = d0 | (512u << 16), dM = d0 | (256u << 16);
      const uint32_t dX = dK + wg * 512;
      constexpr uint32_t RING = OFF_RING >> 4;
      auto waitA = [&](int n) { mbar_wait(bars + 8 * (B_FA + rslot(n)), rpar(n)); };
      auto freeA = [&](int n) { if (elect) mbar_arrive(bars + 8 * (B_EA + rslot(n))); };
      auto nop = [](int) {};

#pragma unroll
      for (int kb = 0; kb < 8; kb++) {
        mbar_wait(bars + 8 * (B_FX + kb), 0); waitA(kb);
        wg_fence();
        const uint64_t dx = d128(dX + kb * 1024), df = d128(dK + RING + rslot(kb) * 1024), dm = d64(dM + RING + 512 + rslot(kb) * 1024);
        if (kb == 0) { mma_ss64<0, 0, 0>(c1, df, dx); mma_ss64<32, 1, 0>(c1, dx, dm); }
        else { mma_ss64<0, 0, 1>(c1, df, dx); mma_ss64<32, 1, 1>(c1, dx, dm); wg_commit(); wg_wait<1>(); freeA(kb - 1); }
#pragma unroll
        for (int k = 1; k < 4; k++) {
          mma_ss64<0, 0, 1>(c1, df + k * 2, dx + k * 2);
          mma_ss64<32, 1, 1>(c1, dx + k * 2, dm + k * 64);
        }
        wg_commit();
        if (kb == 0 && tid == 0) PROF_EV(1);
      }
      auto ffn_step = [&](auto first, float (&acc)[64], int n, int kb, auto done, auto work) {
        waitA(n);
        wg_fence();
        const uint64_t dx = d128(dX + kb * 1024), db = d128(dN + RING + rslot(n) * 1024);
        mma_ss128<0, 1, decltype(first)::value>(acc, dx, db, zero);
        wg_commit();
        wg_wait<1>();
        done();
#pragma unroll
        for (int k = 1; k < 4; k++) { mma_ss128<0, 1, 1>(acc, dx + k * 2, db + k * 128); work(k - 1); }
        wg_commit();
        work(3);
      };
      const uint32_t tag = (ep + 1) & 1;
      float hm[16];
      ffn_step(IC<0>(), c2, 8, 0, [&] { freeA(7); fence_regs<0, 64>(c1); }, [&](int i) {
#pragma unroll
        for (int e = 4 * i; e < 4 * i + 4; e++) { yf[e] = pack_pin(c1[2 * e], c1[2 * e + 1]); hm[e] = fmaxf(c1[32 + e], 0.f) * c1[48 + e]; }
      });
      fence_regs<0, 16>(hm);
      if (tid == 0) PROF_EV(2);
      {
        waitA(9); waitA(10);
        const uint64_t de = d128(dN + RING + (wg ? rslot(10) : rslot(9)) * 1024);
        wg_fence();
        mma_rs128<0, 1, 0>(cA, yf[0], yf[1], yf[2], yf[3], de);
        wg_commit();
        wg_wait<1>();
        freeA(8);
#pragma unroll
        for (int k = 1; k < 4; k++) mma_rs128<0, 1, 1>(cA, yf[4 * k], yf[4 * k + 1], yf[4 * k + 2], yf[4 * k + 3], de + k * 128);
        wg_commit();
      }
      {
        const int s0 = 2 * rb + wg;
        uint2* dst = g_X1p + ((size_t)((2 * j + (w >> 1)) * 8) * 32 + s0) * 64 + (w & 1) * 32 + q * 8 + g;
        auto x1_store = [&](int n) {
          st_u2(dst + n * 2048, (pack_bf16(cA[4 * n] - cA[34 + 4 * n], cA[32 + 4 * n] + cA[4 * n + 2]) & ~1u) | tag,
                pack_bf16(cA[4 * n + 1] - cA[35 + 4 * n], cA[33 + 4 * n] + cA[4 * n + 3]));
        };
        ffn_step(IC<1>(), c2, 11, 1, [&] { freeA(9); freeA(10); fence_regs<0, 64>(cA); }, [&](int i) { x1_store(i); });
        if (tid == 0) PROF_EV(19);
        ffn_step(IC<1>(), c2, 12, 2, [&] { freeA(11); }, [&](int i) { x1_store(4 + i); });
        if (j == 0 && w == 0 && g == 0) {
#pragma unroll
          for (int n = 0; n < 8; n++) {
#pragma unroll
            for (int e = 0; e < 2; e++) {
              st_x2(g_X1s + s0 * 64 + 8 * n + 2 * q + e, tagf(cA[4 * n + e], tag), cA[32 + 4 * n + e]);
              st_x2(g_X1s + (32 + s0) * 64 + 8 * n + 2 * q + e, tagf(cA[4 * n + 2 + e], tag), cA[34 + 4 * n + e]);
            }
          }
        }
        __syncwarp();
        if (lane == 0) hint_add(&g_cntX[32 * j]);
        if (tid == 0) PROF_EV(3);
      }
      const float* gp = g_gate + rb * 128 + wg * 64 + w * 16 + g;
      uint32_t gb0 = ld_x1(gp), gb1 = ld_x1(gp + 8);
#pragma unroll
      for (int kb = 3; kb < 7; kb++) ffn_step(IC<1>(), c2, 10 + kb, kb, [&] { freeA(9 + kb); }, nop);
      {
        const uint32_t t0 = (uint32_t)clock();
        while (__any_sync(0xffffffffu, ((gb0 ^ tag) | (gb1 ^ tag)) & 1)) { gb0 = ld_x1(gp); gb1 = ld_x1(gp + 8); spin_guard(t0); }
      }
      const float g0 = __uint_as_float(gb0 & ~1u), g1 = __uint_as_float(gb1 & ~1u);
      const float o0 = 1.0f - g0, o1 = 1.0f - g1;
      ffn_step(IC<1>(), c2, 17, 7, [&] { freeA(16); }, [&](int i) {
        h[48 + 2 * i] = pack_pin(hm[4 * i] * o0, hm[4 * i + 1] * o0); h[49 + 2 * i] = pack_pin(hm[4 * i + 2] * o1, hm[4 * i + 3] * o1);
      });
      auto glu = [&](float (&acc)[64], int ho, int i0, int i1) {
#pragma unroll
        for (int i = i0; i < i1; i++) {
          const float o = (i & 1) ? o1 : o0;
          h[ho + i] = pack_pin(fmaxf(acc[2 * i], 0.f) * acc[32 + 2 * i] * o, fmaxf(acc[2 * i + 1], 0.f) * acc[33 + 2 * i] * o);
        }
      };
      ffn_step(IC<2>(), cA, 18, 0, [&] { freeA(17); fence_regs<0, 64>(c2); }, [&](int i) { glu(c2, 0, 2 * i, 2 * i + 2); });
      if (tid == 0) PROF_EV(4);
      ffn_step(IC<1>(), cA, 19, 1, [&] { freeA(18); }, [&](int i) { glu(c2, 0, 8 + 2 * i, 10 + 2 * i); });
#pragma unroll
      for (int kb = 2; kb < 8; kb++) ffn_step(IC<1>(), cA, 18 + kb, kb, [&] { freeA(17 + kb); }, nop);
      ffn_step(IC<2>(), c2, 26, 0, [&] { freeA(25); fence_regs<0, 64>(cA); }, [&](int i) { glu(cA, 16, 2 * i, 2 * i + 2); });
      if (tid == 0) PROF_EV(5);
      ffn_step(IC<1>(), c2, 27, 1, [&] { freeA(26); }, [&](int i) { glu(cA, 16, 8 + 2 * i, 10 + 2 * i); });
#pragma unroll
      for (int kb = 2; kb < 8; kb++)
        ffn_step(IC<1>(), c2, 26 + kb, kb, [&] {
          if (kb < 6) freeA(25 + kb);
          if (kb >= 3 && (kb & 1) && elect) mbar_arrive(bars + 8 * (B_ET + ((kb - 3) >> 1)));
        }, nop);
      wg_wait<0>();
      if (elect) mbar_arrive(bars + 8 * (B_ET + 3));
      fence_regs<0, 64>(c2);
      glu(c2, 32, 0, 16);
      if (wg) waitA(35); else waitA(34);
      if (tid == 0) PROF_EV(6);
      mbar_wait(bars + 8 * B_T, 0);
      if (tid == 0) PROF_EV(7);
      wg_fence();
      {
        const uint64_t dt = d128(dN + (OFF_T >> 4) + wg * 512), de = d128(dK + RING + (wg ? rslot(35) : rslot(34)) * 1024);
        mma_ss64<0, 1, 0>(ci, de, dt);
        mma_ss64<32, 1, 0>(ci, de + 512, dt);
#pragma unroll
        for (int k = 1; k < 4; k++) {
          mma_ss64<0, 1, 1>(ci, de + k * 2, dt + k * 128);
          mma_ss64<32, 1, 1>(ci, de + (512 + k * 2), dt + k * 128);
        }
      }
      wg_commit();

      auto head = [&](auto off, int t) {
        constexpr int O = decltype(off)::value;
        mbar_wait(bars + 8 * (B_FT + (t & 3)), t >> 2);
        const uint64_t db = d128(dN + (t & 3) * (TB >> 4));
        wg_fence();
        mma_rs64<O, 1, 0>(ct, h[0], h[1], h[2], h[3], db);
#pragma unroll
        for (int k = 1; k < 6; k++) mma_rs64<O, 1, 1>(ct, h[4 * k], h[4 * k + 1], h[4 * k + 2], h[4 * k + 3], db + k * 128);
        wg_commit();
        wg_wait<1>();
      };
      auto rest = [&](auto off, int t) {
        constexpr int O = decltype(off)::value;
        const uint64_t db = d128(dN + (t & 3) * (TB >> 4));
        wg_fence();
#pragma unroll
        for (int k = 6; k < 14; k++) mma_rs64<O, 1, 1>(ct, h[4 * k], h[4 * k + 1], h[4 * k + 2], h[4 * k + 3], db + k * 128);
#pragma unroll
        for (int k = 0; k < 4; k++) mma_rs64<O, 1, 1>(ct, yf[4 * k], yf[4 * k + 1], yf[4 * k + 2], yf[4 * k + 3], db + (14 + k) * 128);
        wg_commit();
      };
      auto freeT = [&](int t) { if (elect) mbar_arrive(bars + 8 * (B_ET + t)); };
      const uint32_t peerZ = mapa(sb + OFF_Z + tid * 16, rank ^ 1), peerB = mapa(bars + 8 * B_Z, rank ^ 1);
      auto send_peer = [&](auto off, int z) {
        constexpr int O = decltype(off)::value;
        fence_regs<O, 32>(ct);
#pragma unroll
        for (int i = 0; i < 4; i++)
          asm volatile("st.async.weak.shared::cluster.mbarrier::complete_tx::bytes.v4.b32 [%0], {%1,%2,%3,%4}, [%5];" ::"r"(peerZ + z * U + i * 4096),
                       "r"(pack_bf16(ct[O + 8 * i], ct[O + 8 * i + 1])), "r"(pack_bf16(ct[O + 8 * i + 2], ct[O + 8 * i + 3])),
                       "r"(pack_bf16(ct[O + 8 * i + 4], ct[O + 8 * i + 5])), "r"(pack_bf16(ct[O + 8 * i + 6], ct[O + 8 * i + 7])), "r"(peerB + 8 * z) : "memory");
      };
      auto send_grid = [&](auto off, int z) {
        constexpr int O = decltype(off)::value;
        fence_regs<O, 32>(ct);
        mbar_wait(bars + 8 * (B_Z + z), 0);
        uint4* dst = g_part + (size_t)((rb * 8 + 2 * ((q4 + z + 1) & 3) + rank) * 3 + z) * 1024 + tid;
#pragma unroll
        for (int i = 0; i < 4; i++) {
          const uint4 p = *(const uint4*)(smem + OFF_Z + z * U + i * 4096 + tid * 16);
          st_x4(dst + i * 256, (pack_bf16(ct[O + 8 * i] + bf_lo(p.x), ct[O + 8 * i + 1] + bf_hi(p.x)) & ~1u) | tag,
                pack_bf16(ct[O + 8 * i + 2] + bf_lo(p.y), ct[O + 8 * i + 3] + bf_hi(p.y)),
                pack_bf16(ct[O + 8 * i + 4] + bf_lo(p.z), ct[O + 8 * i + 5] + bf_hi(p.z)),
                pack_bf16(ct[O + 8 * i + 6] + bf_lo(p.w), ct[O + 8 * i + 7] + bf_hi(p.w)));
        }
        __syncwarp();
        if (lane == 0) hint_add(&g_cntP[32 * (rb * 8 + 2 * ((q4 + z + 1) & 3) + rank) + z]);
      };
      asm volatile("barrier.cluster.wait.aligned;" ::: "memory");
      head(IC<0>(), 0);
      if (elect) asm volatile("mbarrier.arrive.shared::cluster.b64 _, [%0];" ::"r"(mapa(bars + 8 * B_RDY, rank ^ 1)) : "memory");
      fence_regs<0, 64>(ci);
#pragma unroll
      for (int i = 0; i < 16; i++) {
        const float gg = (i & 1) ? g1 : g0;
        yf[i] = pack_pin((ci[2 * i] + ci[33 + 2 * i]) * gg, (ci[2 * i + 1] - ci[32 + 2 * i]) * gg);
      }
      rest(IC<0>(), 0);
      if (tid == 0) PROF_EV(8);
      head(IC<32>(), 1); freeT(0); mbar_wait(bars + 8 * B_RDY, 0); send_peer(IC<0>(), 0); rest(IC<32>(), 1);
      head(IC<0>(), 2); freeT(1); send_peer(IC<32>(), 1); rest(IC<0>(), 2);
      head(IC<32>(), 3); freeT(2); send_peer(IC<0>(), 2); rest(IC<32>(), 3);
      head(IC<0>(), 4); freeT(3); send_grid(IC<32>(), 0); rest(IC<0>(), 4);
      head(IC<32>(), 5); send_grid(IC<0>(), 1); rest(IC<32>(), 5);
      head(IC<0>(), 6); send_grid(IC<32>(), 2); rest(IC<0>(), 6);
      head(IC<32>(), 7); send_peer(IC<0>(), 3);
      {
        const uint4* src = g_part + (size_t)(rb * 8 + j) * 3 * 1024 + tid;
        uint4 pv[12];
        mbar_wait(bars + 8 * (B_HP + 1), 0);
#pragma unroll
        for (int i = 0; i < 8; i++) pv[i] = ld_x4(src + i * 256);
        rest(IC<32>(), 7);
        if (tid == 0) PROF_EV(9);
        mbar_wait(bars + 8 * (B_HP + 2), 0);
        if (tid == 0) PROF_EV(24);
#pragma unroll
        for (int i = 8; i < 12; i++) pv[i] = ld_x4(src + i * 256);
        const uint32_t t0 = (uint32_t)clock();
        for (;;) {
          uint32_t bad = 0;
#pragma unroll
          for (int i = 0; i < 12; i++) bad |= pv[i].x ^ tag;
          if (!__any_sync(0xffffffffu, bad & 1)) break;
#pragma unroll
          for (int i = 0; i < 12; i++) pv[i] = ld_x4(src + i * 256);
          spin_guard(t0);
        }
        if (tid == 0) PROF_EV(14);
        float sum[32];
#pragma unroll
        for (int i = 0; i < 4; i++) {
          const uint32_t a[4] = {pv[i].x & ~1u, pv[i].y, pv[i].z, pv[i].w}, b[4] = {pv[4 + i].x & ~1u, pv[4 + i].y, pv[4 + i].z, pv[4 + i].w},
                         c[4] = {pv[8 + i].x & ~1u, pv[8 + i].y, pv[8 + i].z, pv[8 + i].w};
#pragma unroll
          for (int e = 0; e < 4; e++) {
            sum[8 * i + 2 * e] = bf_lo(a[e]) + bf_lo(b[e]) + bf_lo(c[e]);
            sum[8 * i + 2 * e + 1] = bf_hi(a[e]) + bf_hi(b[e]) + bf_hi(c[e]);
          }
        }
        mbar_wait(bars + 8 * (B_Z + 3), 0);
#pragma unroll
        for (int i = 0; i < 4; i++) {
          const uint4 p = *(const uint4*)(smem + OFF_Z + 3 * U + i * 4096 + tid * 16);
          const uint32_t a[4] = {p.x, p.y, p.z, p.w};
#pragma unroll
          for (int e = 0; e < 4; e++) { sum[8 * i + 2 * e] += bf_lo(a[e]); sum[8 * i + 2 * e + 1] += bf_hi(a[e]); }
        }
        wg_wait<0>();
        fence_regs<32, 32>(ct);
#pragma unroll
        for (int i = 0; i < 32; i++) sum[i] += ct[32 + i];
        const uint32_t stg = sb + OFF_T + warp * 2048;
        const int mr = (lane & 7) + ((lane >> 3) & 1) * 8, mc = lane >> 4;
#pragma unroll
        for (int i = 0; i < 4; i++) {
          const uint32_t a = stg + mr * 128 + (((2 * i + mc) ^ (mr & 7)) << 4);
          asm volatile("stmatrix.sync.aligned.m8n8.x4.shared.b16 [%0], {%1,%2,%3,%4};" ::"r"(a), "r"(pack_bf16(sum[8 * i], sum[8 * i + 1])),
                       "r"(pack_bf16(sum[8 * i + 2], sum[8 * i + 3])), "r"(pack_bf16(sum[8 * i + 4], sum[8 * i + 5])),
                       "r"(pack_bf16(sum[8 * i + 6], sum[8 * i + 7])) : "memory");
        }
        __syncwarp();
#pragma unroll
        for (int i = 0; i < 4; i++) {
          const int r = 4 * i + (lane >> 3), c = lane & 7;
          const uint4 v = *(const uint4*)(smem + OFF_T + warp * 2048 + r * 128 + ((c ^ (r & 7)) << 4));
          *(uint4*)(out + (size_t)(2 * rb + wg + 32 * (16 * w + r)) * 512 + 64 * j + 8 * c) = v;
        }
      }
      if (tid == 0) { g_epoch[blockIdx.x * 8] = ep + 1; PROF_EV(15); PROF_CK(41); }
    }
  }
}

typedef CUresult (*EncodeFn)(CUtensorMap*, CUtensorMapDataType, cuuint32_t, void*, const cuuint64_t*, const cuuint64_t*, const cuuint32_t*,
                             const cuuint32_t*, CUtensorMapInterleave, CUtensorMapSwizzle, CUtensorMapL2promotion, CUtensorMapFloatOOBfill);

static void encode(EncodeFn f, CUtensorMap* m, const void* base, int rank, const cuuint64_t* dims, const cuuint64_t* strides, const cuuint32_t* box,
                   CUtensorMapSwizzle sw) {
  cuuint32_t es[5] = {1, 1, 1, 1, 1};
  f(m, CU_TENSOR_MAP_DATA_TYPE_BFLOAT16, rank, (void*)base, dims, strides, box, es, CU_TENSOR_MAP_INTERLEAVE_NONE, sw,
    CU_TENSOR_MAP_L2_PROMOTION_L2_128B, CU_TENSOR_MAP_FLOAT_OOB_FILL_NONE);
}

extern "C" void kernel_launch(void* const* d_in, const int* in_sizes, int n_in, void* d_out, int out_size) {
  (void)in_sizes; (void)n_in; (void)out_size;
  const __nv_bfloat16* x = (const __nv_bfloat16*)d_in[0];
  const __nv_bfloat16* w_r = (const __nv_bfloat16*)d_in[1];
  const __nv_bfloat16* w_i = (const __nv_bfloat16*)d_in[2];
  const __nv_bfloat16* Wg = (const __nv_bfloat16*)d_in[4];
  const __nv_bfloat16* Wu = (const __nv_bfloat16*)d_in[5];
  const __nv_bfloat16* Wd = (const __nv_bfloat16*)d_in[6];
  const __nv_bfloat16* gw = (const __nv_bfloat16*)d_in[7];

  void* fp = nullptr; cudaDriverEntryPointQueryResult qr;
  cudaGetDriverEntryPoint("cuTensorMapEncodeTiled", &fp, cudaEnableDefault, &qr);
  EncodeFn enc = (EncodeFn)fp;
  void *pFT, *pET;
  cudaGetSymbolAddress(&pFT, g_FT); cudaGetSymbolAddress(&pET, g_ET);

  Maps mp;
  const CUtensorMapSwizzle S128 = CU_TENSOR_MAP_SWIZZLE_128B, S64 = CU_TENSOR_MAP_SWIZZLE_64B;
  { cuuint64_t d[3] = {512, 64, 32}, s[2] = {32768, 1024}; cuuint32_t b[3] = {64, 64, 2}; encode(enc, &mp.x, x, 3, d, s, b, S128); }
  { cuuint64_t d[2] = {512, 512}, s[1] = {1024}; cuuint32_t b[2] = {64, 64}; encode(enc, &mp.ft, pFT, 2, d, s, b, S128); }
  { cuuint64_t d[4] = {512, 2, 8, 32}, s[3] = {8192, 1024, 16384}; cuuint32_t b[4] = {64, 2, 8, 4}; encode(enc, &mp.fg, pFT, 4, d, s, b, S128); }
  { cuuint64_t d[4] = {64, 64, 2, 32}, s[3] = {8192, 128, 256}; cuuint32_t b[4] = {64, 64, 2, 1}; encode(enc, &mp.e, pET, 4, d, s, b, S128); }
  { cuuint64_t d[2] = {1792, 512}, s[1] = {3584}; cuuint32_t b[2] = {64, 64}, b2[2] = {32, 64};
    encode(enc, &mp.g64, Wg, 2, d, s, b, S128); encode(enc, &mp.u64, Wu, 2, d, s, b, S128);
    encode(enc, &mp.g32, Wg, 2, d, s, b2, S64); encode(enc, &mp.u32, Wu, 2, d, s, b2, S64); }
  { cuuint64_t d[2] = {512, 1792}, s[1] = {1024}; cuuint32_t b[2] = {64, 192}, b2[2] = {64, 32};
    encode(enc, &mp.d192, Wd, 2, d, s, b, S128); encode(enc, &mp.d32, Wd, 2, d, s, b2, S128); }

  { cuuint64_t d[4] = {264, 8, 8, 32}, s[3] = {512, 4112, 32896}; cuuint32_t b[4] = {24, 8, 1, 8};
    encode(enc, &mp.wr, w_r, 4, d, s, b, CU_TENSOR_MAP_SWIZZLE_NONE); encode(enc, &mp.wi, w_i, 4, d, s, b, CU_TENSOR_MAP_SWIZZLE_NONE); }

  cudaFuncSetAttribute(fused_kernel, cudaFuncAttributeMaxDynamicSharedMemorySize, SMEM_BYTES);
  fused_kernel<<<NCTA, 512, SMEM_BYTES>>>(mp, x, w_r, w_i, gw, Wd, (__nv_bfloat16*)d_out);
}
```

```cpp
#include <cuda_runtime.h>
#include <cuda_bf16.h>
#include <cuda.h>
#include <stdint.h>

namespace tbl {
constexpr double PI = 3.14159265358979323846264338327950288;
constexpr double sin_s(double x) { double t = x, s = x; for (int n = 1; n < 12; n++) { t *= -x * x / ((2 * n) * (2 * n + 1)); s += t; } return s; }
constexpr double cos_s(double x) { double t = 1, s = 1; for (int n = 1; n < 12; n++) { t *= -x * x / ((2 * n - 1) * (2 * n)); s += t; } return s; }
constexpr double cos2048(int m) {
  m &= 2047; if (m > 1024) m = 2048 - m;
  bool neg = false; if (m > 512) { m = 1024 - m; neg = true; }
  double v = (m <= 256) ? cos_s(2 * PI * m / 2048) : sin_s(2 * PI * (512 - m) / 2048);
  return neg ? -v : v;
}
constexpr uint16_t to_bf16(double v) {
  if (v == 0) return 0;
  uint16_t s = 0; if (v < 0) { s = 0x8000; v = -v; }
  int e = 0; while (v >= 2) { v /= 2; e++; } while (v < 1) { v *= 2; e--; }
  double m = (v - 1) * 128; int mi = (int)m; double fr = m - mi;
  if (fr > 0.5 || (fr == 0.5 && (mi & 1))) mi++;
  if (mi == 128) { mi = 0; e++; }
  return (uint16_t)(s | ((e + 127) << 7) | mi);
}
struct CosT { uint16_t v[2048]; constexpr CosT() : v() { for (int i = 0; i < 2048; i++) v[i] = to_bf16(cos2048(i)); } };
struct alignas(1024) FT {
  uint16_t v[512 * 512];
  constexpr FT() : v() {
    CosT c;
    for (int r = 0; r < 512; r++) {
      int k = (r >> 4) * 8 + (r & 7), e = (r >> 3) & 1;
      int mul = 4 * k, add = e ? 512 : 0;
      if (k == 0 && e == 1) { mul = 1024; add = 0; }
      for (int d = 0; d < 512; d++) v[r * 512 + d] = c.v[(d * mul + add) & 2047];
    }
  }
};
struct alignas(1024) ET {
  uint16_t v[2048 * 128];
  constexpr ET() : v() {
    CosT c;
    for (int s = 0; s < 2048; s++)
      for (int j = 0; j < 64; j++) { v[s * 128 + j] = c.v[(s * j) & 2047]; v[s * 128 + 64 + j] = c.v[(s * j + 512) & 2047]; }
  }
};
template <int A> struct W32 {
  static constexpr float c = (float)cos2048(A * 64);
  static constexpr float s = (float)cos2048(A * 64 - 512);
};
}

__device__ constexpr tbl::FT g_FT = tbl::FT();
__device__ constexpr tbl::ET g_ET = tbl::ET();

__device__ __align__(1024) uint2 g_X1p[128 * 32 * 64];
__device__ __align__(1024) uint2 g_X1s[32 * 64];
__device__ __align__(1024) uint2 g_T[8 * 16 * 2 * 64 * 16];
__device__ __align__(1024) uint4 g_part[128 * 3 * 1024];
__device__ __align__(16) float g_gate[16 * 128];
__device__ __align__(16) uint2 g_Wh[2 * 2048];
__device__ unsigned g_epoch[132 * 8];
__device__ unsigned g_cntX[8 * 32], g_cntT[8 * 32], g_cntP[128 * 32], g_cntW[32];
#define PROF_EV(i) do {} while (0)
#define PROF_CK(i) do {} while (0)

__device__ __forceinline__ uint32_t smem_u32(const void* p) { return (uint32_t)__cvta_generic_to_shared(p); }
__device__ __forceinline__ void mbar_init(uint32_t bar, uint32_t cnt) { asm volatile("mbarrier.init.shared::cta.b64 [%0], %1;" ::"r"(bar), "r"(cnt)); }
__device__ __forceinline__ void mbar_expect_tx(uint32_t bar, uint32_t bytes) { asm volatile("mbarrier.arrive.expect_tx.shared::cta.b64 _, [%0], %1;" ::"r"(bar), "r"(bytes) : "memory"); }
__device__ __forceinline__ void mbar_arrive(uint32_t bar) { asm volatile("mbarrier.arrive.shared::cta.b64 _, [%0];" ::"r"(bar) : "memory"); }
__device__ __forceinline__ void mbar_wait(uint32_t bar, uint32_t parity) {
  asm volatile(
      "{\n.reg .pred p;\n.reg .u32 n;\nmov.u32 n, 0;\n"
      "W_LOOP:\nmbarrier.try_wait.parity.shared::cta.b64 p, [%0], %1, 2000;\n@p bra W_DONE;\n"
      "add.u32 n, n, 1;\nsetp.lt.u32 p, n, 0x800000;\n@p bra W_LOOP;\ntrap;\nW_DONE:\n}" ::"r"(bar), "r"(parity) : "memory");
}
__device__ __forceinline__ void cp16(uint32_t dst, const void* src) { asm volatile("cp.async.cg.shared.global [%0], [%1], 16;" ::"r"(dst), "l"(src) : "memory"); }
__device__ __forceinline__ void spin_guard(uint32_t t0) { if ((uint32_t)clock() - t0 > (1u << 30)) __trap(); }
__device__ __forceinline__ float tagf(float v, uint32_t tag) { return __uint_as_float((__float_as_uint(v) & ~1u) | tag); }
__device__ __forceinline__ float untag(float v) { return __uint_as_float(__float_as_uint(v) & ~1u); }
__device__ __forceinline__ void st_x2(float2* p, float a, float b) { asm volatile("st.relaxed.gpu.global.v2.f32 [%0], {%1,%2};" ::"l"(p), "f"(a), "f"(b) : "memory"); }
__device__ __forceinline__ float2 ld_x2(const float2* p) { float2 v; asm volatile("ld.relaxed.gpu.global.v2.f32 {%0,%1}, [%2];" : "=f"(v.x), "=f"(v.y) : "l"(p) : "memory"); return v; }
__device__ __forceinline__ void st_u2(uint2* p, uint32_t a, uint32_t b) { asm volatile("st.relaxed.gpu.global.v2.u32 [%0], {%1,%2};" ::"l"(p), "r"(a), "r"(b) : "memory"); }
__device__ __forceinline__ void prefetch2d(const CUtensorMap* m, int c0, int c1) { asm volatile("cp.async.bulk.prefetch.tensor.2d.L2.global [%0, {%1, %2}];" ::"l"(m), "r"(c0), "r"(c1) : "memory"); }
__device__ __forceinline__ void prefetch1d(const void* p, uint32_t bytes) { asm volatile("cp.async.bulk.prefetch.L2.global [%0], %1;" ::"l"(p), "r"(bytes) : "memory"); }
__device__ __forceinline__ uint32_t ld_x1(const void* p) { uint32_t v; asm volatile("ld.relaxed.gpu.global.u32 %0, [%1];" : "=r"(v) : "l"(p) : "memory"); return v; }
__device__ __forceinline__ uint4 ld_x4(const void* p) { uint4 v; asm volatile("ld.relaxed.gpu.global.v4.u32 {%0,%1,%2,%3}, [%4];" : "=r"(v.x), "=r"(v.y), "=r"(v.z), "=r"(v.w) : "l"(p) : "memory"); return v; }
__device__ __forceinline__ void st_x4(void* p, uint32_t a, uint32_t b, uint32_t c, uint32_t d) { asm volatile("st.relaxed.gpu.global.v4.u32 [%0], {%1,%2,%3,%4};" ::"l"(p), "r"(a), "r"(b), "r"(c), "r"(d) : "memory"); }
__device__ __forceinline__ uint32_t mapa(uint32_t a, uint32_t cta) { uint32_t r; asm volatile("mapa.shared::cluster.u32 %0, %1, %2;" : "=r"(r) : "r"(a), "r"(cta)); return r; }
__device__ __forceinline__ void hint_add(unsigned* p) { asm volatile("red.relaxed.gpu.global.add.u32 [%0], 1;" ::"l"(p) : "memory"); }
__device__ __forceinline__ void hint_wait(const unsigned* p, unsigned target) {
  const uint32_t t0 = (uint32_t)clock();
  while ((int)(ld_x1(p) - target) < 0) spin_guard(t0);
}
__device__ __forceinline__ void tma2d(uint32_t dst, const CUtensorMap* m, uint32_t bar, int c0, int c1) {
  asm volatile("cp.async.bulk.tensor.2d.shared::cluster.global.mbarrier::complete_tx::bytes [%0], [%1, {%3, %4}], [%2];" ::"r"(dst), "l"(m), "r"(bar), "r"(c0), "r"(c1) : "memory");
}
__device__ __forceinline__ void tma3d(uint32_t dst, const CUtensorMap* m, uint32_t bar, int c0, int c1, int c2) {
  asm volatile("cp.async.bulk.tensor.3d.shared::cluster.global.mbarrier::complete_tx::bytes [%0], [%1, {%3, %4, %5}], [%2];" ::"r"(dst), "l"(m), "r"(bar), "r"(c0), "r"(c1), "r"(c2) : "memory");
}
__device__ __forceinline__ void tma4d(uint32_t dst, const CUtensorMap* m, uint32_t bar, int c0, int c1, int c2, int c3) {
  asm volatile("cp.async.bulk.tensor.4d.shared::cluster.global.mbarrier::complete_tx::bytes [%0], [%1, {%3, %4, %5, %6}], [%2];" ::"r"(dst), "l"(m), "r"(bar), "r"(c0), "r"(c1), "r"(c2), "r"(c3) : "memory");
}
__device__ __forceinline__ void wg_fence() { asm volatile("wgmma.fence.sync.aligned;" ::: "memory"); }
__device__ __forceinline__ void wg_commit() { asm volatile("wgmma.commit_group.sync.aligned;" ::: "memory"); }
template <int N> __device__ __forceinline__ void wg_wait() { asm volatile("wgmma.wait_group.sync.aligned %0;" ::"n"(N) : "memory"); }
template <int O, int N, int NN> __device__ __forceinline__ void fence_regs(float (&d)[NN]) {
#pragma unroll
  for (int i = 0; i < N; i++) asm volatile("" : "+f"(d[O + i])::"memory");
}
__device__ __forceinline__ uint32_t pack_bf16(float lo, float hi) {
  uint32_t r; asm("cvt.rn.bf16x2.f32 %0, %1, %2;" : "=r"(r) : "f"(hi), "f"(lo)); return r;
}
__device__ __forceinline__ uint32_t pack_pin(float lo, float hi) {
  uint32_t r; asm volatile("cvt.rn.bf16x2.f32 %0, %1, %2;" : "=r"(r) : "f"(hi), "f"(lo) : "memory"); return r;
}
__device__ __forceinline__ float bf_lo(uint32_t u) { return __uint_as_float(u << 16); }
__device__ __forceinline__ float bf_hi(uint32_t u) { return __uint_as_float(u & 0xffff0000u); }

__device__ __forceinline__ uint64_t d128(uint32_t lo) { uint64_t d; asm("mov.b64 %0, {%1, 0x40000040};" : "=l"(d) : "r"(lo)); return d; }
__device__ __forceinline__ uint64_t d64(uint32_t lo) { uint64_t d; asm("mov.b64 %0, {%1, 0x80000020};" : "=l"(d) : "r"(lo)); return d; }
template<int O,int TB,int ACC,int NN> __device__ __forceinline__ void mma_ss64(float (&d)[NN], uint64_t da, uint64_t db, int sd = 0){
  if constexpr (ACC == 1) asm volatile("wgmma.mma_async.sync.aligned.m64n64k16.f32.bf16.bf16 {%0,%1,%2,%3,%4,%5,%6,%7,%8,%9,%10,%11,%12,%13,%14,%15,%16,%17,%18,%19,%20,%21,%22,%23,%24,%25,%26,%27,%28,%29,%30,%31}, %32, %33, 1, 1, 1, 0, %34;"
   : "+f"(d[O+0]), "+f"(d[O+1]), "+f"(d[O+2]), "+f"(d[O+3]), "+f"(d[O+4]), "+f"(d[O+5]), "+f"(d[O+6]), "+f"(d[O+7]), "+f"(d[O+8]), "+f"(d[O+9]), "+f"(d[O+10]), "+f"(d[O+11]), "+f"(d[O+12]), "+f"(d[O+13]), "+f"(d[O+14]), "+f"(d[O+15]), "+f"(d[O+16]), "+f"(d[O+17]), "+f"(d[O+18]), "+f"(d[O+19]), "+f"(d[O+20]), "+f"(d[O+21]), "+f"(d[O+22]), "+f"(d[O+23]), "+f"(d[O+24]), "+f"(d[O+25]), "+f"(d[O+26]), "+f"(d[O+27]), "+f"(d[O+28]), "+f"(d[O+29]), "+f"(d[O+30]), "+f"(d[O+31])
   : "l"(da), "l"(db), "n"(TB));
  else if constexpr (ACC == 0) asm volatile("wgmma.mma_async.sync.aligned.m64n64k16.f32.bf16.bf16 {%0,%1,%2,%3,%4,%5,%6,%7,%8,%9,%10,%11,%12,%13,%14,%15,%16,%17,%18,%19,%20,%21,%22,%23,%24,%25,%26,%27,%28,%29,%30,%31}, %32, %33, 0, 1, 1, 0, %34;"
   : "=f"(d[O+0]), "=f"(d[O+1]), "=f"(d[O+2]), "=f"(d[O+3]), "=f"(d[O+4]), "=f"(d[O+5]), "=f"(d[O+6]), "=f"(d[O+7]), "=f"(d[O+8]), "=f"(d[O+9]), "=f"(d[O+10]), "=f"(d[O+11]), "=f"(d[O+12]), "=f"(d[O+13]), "=f"(d[O+14]), "=f"(d[O+15]), "=f"(d[O+16]), "=f"(d[O+17]), "=f"(d[O+18]), "=f"(d[O+19]), "=f"(d[O+20]), "=f"(d[O+21]), "=f"(d[O+22]), "=f"(d[O+23]), "=f"(d[O+24]), "=f"(d[O+25]), "=f"(d[O+26]), "=f"(d[O+27]), "=f"(d[O+28]), "=f"(d[O+29]), "=f"(d[O+30]), "=f"(d[O+31])
   : "l"(da), "l"(db), "n"(TB));
  else asm volatile("{\n.reg .pred p;\nsetp.ne.b32 p, %35, 0;\nwgmma.mma_async.sync.aligned.m64n64k16.f32.bf16.bf16 {%0,%1,%2,%3,%4,%5,%6,%7,%8,%9,%10,%11,%12,%13,%14,%15,%16,%17,%18,%19,%20,%21,%22,%23,%24,%25,%26,%27,%28,%29,%30,%31}, %32, %33, p, 1, 1, 0, %34;\n}"
   : "+f"(d[O+0]), "+f"(d[O+1]), "+f"(d[O+2]), "+f"(d[O+3]), "+f"(d[O+4]), "+f"(d[O+5]), "+f"(d[O+6]), "+f"(d[O+7]), "+f"(d[O+8]), "+f"(d[O+9]), "+f"(d[O+10]), "+f"(d[O+11]), "+f"(d[O+12]), "+f"(d[O+13]), "+f"(d[O+14]), "+f"(d[O+15]), "+f"(d[O+16]), "+f"(d[O+17]), "+f"(d[O+18]), "+f"(d[O+19]), "+f"(d[O+20]), "+f"(d[O+21]), "+f"(d[O+22]), "+f"(d[O+23]), "+f"(d[O+24]), "+f"(d[O+25]), "+f"(d[O+26]), "+f"(d[O+27]), "+f"(d[O+28]), "+f"(d[O+29]), "+f"(d[O+30]), "+f"(d[O+31])
   : "l"(da), "l"(db), "n"(TB), "r"(sd));
}
template<int O,int TB,int ACC,int NN> __device__ __forceinline__ void mma_rs64(float (&d)[NN], uint32_t a0, uint32_t a1, uint32_t a2, uint32_t a3, uint64_t db, int sd = 0){
  if constexpr (ACC == 1) asm volatile("wgmma.mma_async.sync.aligned.m64n64k16.f32.bf16.bf16 {%0,%1,%2,%3,%4,%5,%6,%7,%8,%9,%10,%11,%12,%13,%14,%15,%16,%17,%18,%19,%20,%21,%22,%23,%24,%25,%26,%27,%28,%29,%30,%31}, {%32,%33,%34,%35}, %36, 1, 1, 1, %37;"
   : "+f"(d[O+0]), "+f"(d[O+1]), "+f"(d[O+2]), "+f"(d[O+3]), "+f"(d[O+4]), "+f"(d[O+5]), "+f"(d[O+6]), "+f"(d[O+7]), "+f"(d[O+8]), "+f"(d[O+9]), "+f"(d[O+10]), "+f"(d[O+11]), "+f"(d[O+12]), "+f"(d[O+13]), "+f"(d[O+14]), "+f"(d[O+15]), "+f"(d[O+16]), "+f"(d[O+17]), "+f"(d[O+18]), "+f"(d[O+19]), "+f"(d[O+20]), "+f"(d[O+21]), "+f"(d[O+22]), "+f"(d[O+23]), "+f"(d[O+24]), "+f"(d[O+25]), "+f"(d[O+26]), "+f"(d[O+27]), "+f"(d[O+28]), "+f"(d[O+29]), "+f"(d[O+30]), "+f"(d[O+31])
   : "r"(a0), "r"(a1), "r"(a2), "r"(a3), "l"(db), "n"(TB));
  else if constexpr (ACC == 0) asm volatile("wgmma.mma_async.sync.aligned.m64n64k16.f32.bf16.bf16 {%0,%1,%2,%3,%4,%5,%6,%7,%8,%9,%10,%11,%12,%13,%14,%15,%16,%17,%18,%19,%20,%21,%22,%23,%24,%25,%26,%27,%28,%29,%30,%31}, {%32,%33,%34,%35}, %36, 0, 1, 1, %37;"
   : "=f"(d[O+0]), "=f"(d[O+1]), "=f"(d[O+2]), "=f"(d[O+3]), "=f"(d[O+4]), "=f"(d[O+5]), "=f"(d[O+6]), "=f"(d[O+7]), "=f"(d[O+8]), "=f"(d[O+9]), "=f"(d[O+10]), "=f"(d[O+11]), "=f"(d[O+12]), "=f"(d[O+13]), "=f"(d[O+14]), "=f"(d[O+15]), "=f"(d[O+16]), "=f"(d[O+17]), "=f"(d[O+18]), "=f"(d[O+19]), "=f"(d[O+20]), "=f"(d[O+21]), "=f"(d[O+22]), "=f"(d[O+23]), "=f"(d[O+24]), "=f"(d[O+25]), "=f"(d[O+26]), "=f"(d[O+27]), "=f"(d[O+28]), "=f"(d[O+29]), "=f"(d[O+30]), "=f"(d[O+31])
   : "r"(a0), "r"(a1), "r"(a2), "r"(a3), "l"(db), "n"(TB));
  else asm volatile("{\n.reg .pred p;\nsetp.ne.b32 p, %38, 0;\nwgmma.mma_async.sync.aligned.m64n64k16.f32.bf16.bf16 {%0,%1,%2,%3,%4,%5,%6,%7,%8,%9,%10,%11,%12,%13,%14,%15,%16,%17,%18,%19,%20,%21,%22,%23,%24,%25,%26,%27,%28,%29,%30,%31}, {%32,%33,%34,%35}, %36, p, 1, 1, %37;\n}"
   : "+f"(d[O+0]), "+f"(d[O+1]), "+f"(d[O+2]), "+f"(d[O+3]), "+f"(d[O+4]), "+f"(d[O+5]), "+f"(d[O+6]), "+f"(d[O+7]), "+f"(d[O+8]), "+f"(d[O+9]), "+f"(d[O+10]), "+f"(d[O+11]), "+f"(d[O+12]), "+f"(d[O+13]), "+f"(d[O+14]), "+f"(d[O+15]), "+f"(d[O+16]), "+f"(d[O+17]), "+f"(d[O+18]), "+f"(d[O+19]), "+f"(d[O+20]), "+f"(d[O+21]), "+f"(d[O+22]), "+f"(d[O+23]), "+f"(d[O+24]), "+f"(d[O+25]), "+f"(d[O+26]), "+f"(d[O+27]), "+f"(d[O+28]), "+f"(d[O+29]), "+f"(d[O+30]), "+f"(d[O+31])
   : "r"(a0), "r"(a1), "r"(a2), "r"(a3), "l"(db), "n"(TB), "r"(sd));
}
template<int O,int TB,int ACC,int NN> __device__ __forceinline__ void mma_ss128(float (&d)[NN], uint64_t da, uint64_t db, int sd = 0){
  if constexpr (ACC == 1) asm volatile("wgmma.mma_async.sync.aligned.m64n128k16.f32.bf16.bf16 {%0,%1,%2,%3,%4,%5,%6,%7,%8,%9,%10,%11,%12,%13,%14,%15,%16,%17,%18,%19,%20,%21,%22,%23,%24,%25,%26,%27,%28,%29,%30,%31,%32,%33,%34,%35,%36,%37,%38,%39,%40,%41,%42,%43,%44,%45,%46,%47,%48,%49,%50,%51,%52,%53,%54,%55,%56,%57,%58,%59,%60,%61,%62,%63}, %64, %65, 1, 1, 1, 0, %66;"
   : "+f"(d[O+0]), "+f"(d[O+1]), "+f"(d[O+2]), "+f"(d[O+3]), "+f"(d[O+4]), "+f"(d[O+5]), "+f"(d[O+6]), "+f"(d[O+7]), "+f"(d[O+8]), "+f"(d[O+9]), "+f"(d[O+10]), "+f"(d[O+11]), "+f"(d[O+12]), "+f"(d[O+13]), "+f"(d[O+14]), "+f"(d[O+15]), "+f"(d[O+16]), "+f"(d[O+17]), "+f"(d[O+18]), "+f"(d[O+19]), "+f"(d[O+20]), "+f"(d[O+21]), "+f"(d[O+22]), "+f"(d[O+23]), "+f"(d[O+24]), "+f"(d[O+25]), "+f"(d[O+26]), "+f"(d[O+27]), "+f"(d[O+28]), "+f"(d[O+29]), "+f"(d[O+30]), "+f"(d[O+31]), "+f"(d[O+32]), "+f"(d[O+33]), "+f"(d[O+34]), "+f"(d[O+35]), "+f"(d[O+36]), "+f"(d[O+37]), "+f"(d[O+38]), "+f"(d[O+39]), "+f"(d[O+40]), "+f"(d[O+41]), "+f"(d[O+42]), "+f"(d[O+43]), "+f"(d[O+44]), "+f"(d[O+45]), "+f"(d[O+46]), "+f"(d[O+47]), "+f"(d[O+48]), "+f"(d[O+49]), "+f"(d[O+50]), "+f"(d[O+51]), "+f"(d[O+52]), "+f"(d[O+53]), "+f"(d[O+54]), "+f"(d[O+55]), "+f"(d[O+56]), "+f"(d[O+57]), "+f"(d[O+58]), "+f"(d[O+59]), "+f"(d[O+60]), "+f"(d[O+61]), "+f"(d[O+62]), "+f"(d[O+63])
   : "l"(da), "l"(db), "n"(TB));
  else if constexpr (ACC == 0) asm volatile("wgmma.mma_async.sync.aligned.m64n128k16.f32.bf16.bf16 {%0,%1,%2,%3,%4,%5,%6,%7,%8,%9,%10,%11,%12,%13,%14,%15,%16,%17,%18,%19,%20,%21,%22,%23,%24,%25,%26,%27,%28,%29,%30,%31,%32,%33,%34,%35,%36,%37,%38,%39,%40,%41,%42,%43,%44,%45,%46,%47,%48,%49,%50,%51,%52,%53,%54,%55,%56,%57,%58,%59,%60,%61,%62,%63}, %64, %65, 0, 1, 1, 0, %66;"
   : "=f"(d[O+0]), "=f"(d[O+1]), "=f"(d[O+2]), "=f"(d[O+3]), "=f"(d[O+4]), "=f"(d[O+5]), "=f"(d[O+6]), "=f"(d[O+7]), "=f"(d[O+8]), "=f"(d[O+9]), "=f"(d[O+10]), "=f"(d[O+11]), "=f"(d[O+12]), "=f"(d[O+13]), "=f"(d[O+14]), "=f"(d[O+15]), "=f"(d[O+16]), "=f"(d[O+17]), "=f"(d[O+18]), "=f"(d[O+19]), "=f"(d[O+20]), "=f"(d[O+21]), "=f"(d[O+22]), "=f"(d[O+23]), "=f"(d[O+24]), "=f"(d[O+25]), "=f"(d[O+26]), "=f"(d[O+27]), "=f"(d[O+28]), "=f"(d[O+29]), "=f"(d[O+30]), "=f"(d[O+31]), "=f"(d[O+32]), "=f"(d[O+33]), "=f"(d[O+34]), "=f"(d[O+35]), "=f"(d[O+36]), "=f"(d[O+37]), "=f"(d[O+38]), "=f"(d[O+39]), "=f"(d[O+40]), "=f"(d[O+41]), "=f"(d[O+42]), "=f"(d[O+43]), "=f"(d[O+44]), "=f"(d[O+45]), "=f"(d[O+46]), "=f"(d[O+47]), "=f"(d[O+48]), "=f"(d[O+49]), "=f"(d[O+50]), "=f"(d[O+51]), "=f"(d[O+52]), "=f"(d[O+53]), "=f"(d[O+54]), "=f"(d[O+55]), "=f"(d[O+56]), "=f"(d[O+57]), "=f"(d[O+58]), "=f"(d[O+59]), "=f"(d[O+60]), "=f"(d[O+61]), "=f"(d[O+62]), "=f"(d[O+63])
   : "l"(da), "l"(db), "n"(TB));
  else asm volatile("{\n.reg .pred p;\nsetp.ne.b32 p, %67, 0;\nwgmma.mma_async.sync.aligned.m64n128k16.f32.bf16.bf16 {%0,%1,%2,%3,%4,%5,%6,%7,%8,%9,%10,%11,%12,%13,%14,%15,%16,%17,%18,%19,%20,%21,%22,%23,%24,%25,%26,%27,%28,%29,%30,%31,%32,%33,%34,%35,%36,%37,%38,%39,%40,%41,%42,%43,%44,%45,%46,%47,%48,%49,%50,%51,%52,%53,%54,%55,%56,%57,%58,%59,%60,%61,%62,%63}, %64, %65, p, 1, 1, 0, %66;\n}"
   : "+f"(d[O+0]), "+f"(d[O+1]), "+f"(d[O+2]), "+f"(d[O+3]), "+f"(d[O+4]), "+f"(d[O+5]), "+f"(d[O+6]), "+f"(d[O+7]), "+f"(d[O+8]), "+f"(d[O+9]), "+f"(d[O+10]), "+f"(d[O+11]), "+f"(d[O+12]), "+f"(d[O+13]), "+f"(d[O+14]), "+f"(d[O+15]), "+f"(d[O+16]), "+f"(d[O+17]), "+f"(d[O+18]), "+f"(d[O+19]), "+f"(d[O+20]), "+f"(d[O+21]), "+f"(d[O+22]), "+f"(d[O+23]), "+f"(d[O+24]), "+f"(d[O+25]), "+f"(d[O+26]), "+f"(d[O+27]), "+f"(d[O+28]), "+f"(d[O+29]), "+f"(d[O+30]), "+f"(d[O+31]), "+f"(d[O+32]), "+f"(d[O+33]), "+f"(d[O+34]), "+f"(d[O+35]), "+f"(d[O+36]), "+f"(d[O+37]), "+f"(d[O+38]), "+f"(d[O+39]), "+f"(d[O+40]), "+f"(d[O+41]), "+f"(d[O+42]), "+f"(d[O+43]), "+f"(d[O+44]), "+f"(d[O+45]), "+f"(d[O+46]), "+f"(d[O+47]), "+f"(d[O+48]), "+f"(d[O+49]), "+f"(d[O+50]), "+f"(d[O+51]), "+f"(d[O+52]), "+f"(d[O+53]), "+f"(d[O+54]), "+f"(d[O+55]), "+f"(d[O+56]), "+f"(d[O+57]), "+f"(d[O+58]), "+f"(d[O+59]), "+f"(d[O+60]), "+f"(d[O+61]), "+f"(d[O+62]), "+f"(d[O+63])
   : "l"(da), "l"(db), "n"(TB), "r"(sd));
}
template<int O,int TB,int ACC,int NN> __device__ __forceinline__ void mma_rs128(float (&d)[NN], uint32_t a0, uint32_t a1, uint32_t a2, uint32_t a3, uint64_t db, int sd = 0){
  if constexpr (ACC == 1) asm volatile("wgmma.mma_async.sync.aligned.m64n128k16.f32.bf16.bf16 {%0,%1,%2,%3,%4,%5,%6,%7,%8,%9,%10,%11,%12,%13,%14,%15,%16,%17,%18,%19,%20,%21,%22,%23,%24,%25,%26,%27,%28,%29,%30,%31,%32,%33,%34,%35,%36,%37,%38,%39,%40,%41,%42,%43,%44,%45,%46,%47,%48,%49,%50,%51,%52,%53,%54,%55,%56,%57,%58,%59,%60,%61,%62,%63}, {%64,%65,%66,%67}, %68, 1, 1, 1, %69;"
   : "+f"(d[O+0]), "+f"(d[O+1]), "+f"(d[O+2]), "+f"(d[O+3]), "+f"(d[O+4]), "+f"(d[O+5]), "+f"(d[O+6]), "+f"(d[O+7]), "+f"(d[O+8]), "+f"(d[O+9]), "+f"(d[O+10]), "+f"(d[O+11]), "+f"(d[O+12]), "+f"(d[O+13]), "+f"(d[O+14]), "+f"(d[O+15]), "+f"(d[O+16]), "+f"(d[O+17]), "+f"(d[O+18]), "+f"(d[O+19]), "+f"(d[O+20]), "+f"(d[O+21]), "+f"(d[O+22]), "+f"(d[O+23]), "+f"(d[O+24]), "+f"(d[O+25]), "+f"(d[O+26]), "+f"(d[O+27]), "+f"(d[O+28]), "+f"(d[O+29]), "+f"(d[O+30]), "+f"(d[O+31]), "+f"(d[O+32]), "+f"(d[O+33]), "+f"(d[O+34]), "+f"(d[O+35]), "+f"(d[O+36]), "+f"(d[O+37]), "+f"(d[O+38]), "+f"(d[O+39]), "+f"(d[O+40]), "+f"(d[O+41]), "+f"(d[O+42]), "+f"(d[O+43]), "+f"(d[O+44]), "+f"(d[O+45]), "+f"(d[O+46]), "+f"(d[O+47]), "+f"(d[O+48]), "+f"(d[O+49]), "+f"(d[O+50]), "+f"(d[O+51]), "+f"(d[O+52]), "+f"(d[O+53]), "+f"(d[O+54]), "+f"(d[O+55]), "+f"(d[O+56]), "+f"(d[O+57]), "+f"(d[O+58]), "+f"(d[O+59]), "+f"(d[O+60]), "+f"(d[O+61]), "+f"(d[O+62]), "+f"(d[O+63])
   : "r"(a0), "r"(a1), "r"(a2), "r"(a3), "l"(db), "n"(TB));
  else if constexpr (ACC == 0) asm volatile("wgmma.mma_async.sync.aligned.m64n128k16.f32.bf16.bf16 {%0,%1,%2,%3,%4,%5,%6,%7,%8,%9,%10,%11,%12,%13,%14,%15,%16,%17,%18,%19,%20,%21,%22,%23,%24,%25,%26,%27,%28,%29,%30,%31,%32,%33,%34,%35,%36,%37,%38,%39,%40,%41,%42,%43,%44,%45,%46,%47,%48,%49,%50,%51,%52,%53,%54,%55,%56,%57,%58,%59,%60,%61,%62,%63}, {%64,%65,%66,%67}, %68, 0, 1, 1, %69;"
   : "=f"(d[O+0]), "=f"(d[O+1]), "=f"(d[O+2]), "=f"(d[O+3]), "=f"(d[O+4]), "=f"(d[O+5]), "=f"(d[O+6]), "=f"(d[O+7]), "=f"(d[O+8]), "=f"(d[O+9]), "=f"(d[O+10]), "=f"(d[O+11]), "=f"(d[O+12]), "=f"(d[O+13]), "=f"(d[O+14]), "=f"(d[O+15]), "=f"(d[O+16]), "=f"(d[O+17]), "=f"(d[O+18]), "=f"(d[O+19]), "=f"(d[O+20]), "=f"(d[O+21]), "=f"(d[O+22]), "=f"(d[O+23]), "=f"(d[O+24]), "=f"(d[O+25]), "=f"(d[O+26]), "=f"(d[O+27]), "=f"(d[O+28]), "=f"(d[O+29]), "=f"(d[O+30]), "=f"(d[O+31]), "=f"(d[O+32]), "=f"(d[O+33]), "=f"(d[O+34]), "=f"(d[O+35]), "=f"(d[O+36]), "=f"(d[O+37]), "=f"(d[O+38]), "=f"(d[O+39]), "=f"(d[O+40]), "=f"(d[O+41]), "=f"(d[O+42]), "=f"(d[O+43]), "=f"(d[O+44]), "=f"(d[O+45]), "=f"(d[O+46]), "=f"(d[O+47]), "=f"(d[O+48]), "=f"(d[O+49]), "=f"(d[O+50]), "=f"(d[O+51]), "=f"(d[O+52]), "=f"(d[O+53]), "=f"(d[O+54]), "=f"(d[O+55]), "=f"(d[O+56]), "=f"(d[O+57]), "=f"(d[O+58]), "=f"(d[O+59]), "=f"(d[O+60]), "=f"(d[O+61]), "=f"(d[O+62]), "=f"(d[O+63])
   : "r"(a0), "r"(a1), "r"(a2), "r"(a3), "l"(db), "n"(TB));
  else asm volatile("{\n.reg .pred p;\nsetp.ne.b32 p, %70, 0;\nwgmma.mma_async.sync.aligned.m64n128k16.f32.bf16.bf16 {%0,%1,%2,%3,%4,%5,%6,%7,%8,%9,%10,%11,%12,%13,%14,%15,%16,%17,%18,%19,%20,%21,%22,%23,%24,%25,%26,%27,%28,%29,%30,%31,%32,%33,%34,%35,%36,%37,%38,%39,%40,%41,%42,%43,%44,%45,%46,%47,%48,%49,%50,%51,%52,%53,%54,%55,%56,%57,%58,%59,%60,%61,%62,%63}, {%64,%65,%66,%67}, %68, p, 1, 1, %69;\n}"
   : "+f"(d[O+0]), "+f"(d[O+1]), "+f"(d[O+2]), "+f"(d[O+3]), "+f"(d[O+4]), "+f"(d[O+5]), "+f"(d[O+6]), "+f"(d[O+7]), "+f"(d[O+8]), "+f"(d[O+9]), "+f"(d[O+10]), "+f"(d[O+11]), "+f"(d[O+12]), "+f"(d[O+13]), "+f"(d[O+14]), "+f"(d[O+15]), "+f"(d[O+16]), "+f"(d[O+17]), "+f"(d[O+18]), "+f"(d[O+19]), "+f"(d[O+20]), "+f"(d[O+21]), "+f"(d[O+22]), "+f"(d[O+23]), "+f"(d[O+24]), "+f"(d[O+25]), "+f"(d[O+26]), "+f"(d[O+27]), "+f"(d[O+28]), "+f"(d[O+29]), "+f"(d[O+30]), "+f"(d[O+31]), "+f"(d[O+32]), "+f"(d[O+33]), "+f"(d[O+34]), "+f"(d[O+35]), "+f"(d[O+36]), "+f"(d[O+37]), "+f"(d[O+38]), "+f"(d[O+39]), "+f"(d[O+40]), "+f"(d[O+41]), "+f"(d[O+42]), "+f"(d[O+43]), "+f"(d[O+44]), "+f"(d[O+45]), "+f"(d[O+46]), "+f"(d[O+47]), "+f"(d[O+48]), "+f"(d[O+49]), "+f"(d[O+50]), "+f"(d[O+51]), "+f"(d[O+52]), "+f"(d[O+53]), "+f"(d[O+54]), "+f"(d[O+55]), "+f"(d[O+56]), "+f"(d[O+57]), "+f"(d[O+58]), "+f"(d[O+59]), "+f"(d[O+60]), "+f"(d[O+61]), "+f"(d[O+62]), "+f"(d[O+63])
   : "r"(a0), "r"(a1), "r"(a2), "r"(a3), "l"(db), "n"(TB), "r"(sd));
}

__host__ __device__ constexpr int brev(int a, int bits) { int r = 0; for (int i = 0; i < bits; i++) r |= ((a >> i) & 1) << (bits - 1 - i); return r; }
__host__ __device__ constexpr int ilog2(int n) { return n <= 1 ? 0 : 1 + ilog2(n / 2); }
template <int SG, int A> __device__ __forceinline__ void bfly(float2& a, float2& b) {
  if constexpr (A == 0) {
    float tr = a.x - b.x, ti = a.y - b.y; a.x += b.x; a.y += b.y; b.x = tr; b.y = ti;
  } else if constexpr (A == 8) {
    float pr = SG > 0 ? -b.y : b.y, pi = SG > 0 ? b.x : -b.x;
    b.x = a.x - pr; b.y = a.y - pi; a.x += pr; a.y += pi;
  } else {
    constexpr float wr = tbl::W32<A>::c, wi = SG * tbl::W32<A>::s;
    float tr = fmaf(wr, b.x, a.x), ti = fmaf(wr, b.y, a.y);
    tr = fmaf(-wi, b.y, tr); ti = fmaf(wi, b.x, ti);
    b.x = fmaf(2.f, a.x, -tr); b.y = fmaf(2.f, a.y, -ti); a.x = tr; a.y = ti;
  }
}
template <int SG, int N, int O, int ST, int A> __device__ __forceinline__ void dft_comb(float2 (&x)[32]) {
  if constexpr (A < N / 2) {
    constexpr int p = O + 2 * ST * brev(A, ilog2(N / 2));
    bfly<SG, A * (32 / N)>(x[p], x[p + ST]);
    dft_comb<SG, N, O, ST, A + 1>(x);
  }
}
template <int SG, int N, int O, int ST> __device__ __forceinline__ void dft(float2 (&x)[32]) {
  if constexpr (N > 1) {
    dft<SG, N / 2, O, 2 * ST>(x);
    dft<SG, N / 2, O + ST, 2 * ST>(x);
    dft_comb<SG, N, O, ST, 0>(x);
  }
}

#define NEARLY 3
#define XAHEAD 2
#define WAFTER 5
#define WPACE 100
#define TPACE 40
#define PFMODE 0
#define MAPMODE 0
template <int V> struct IC { static constexpr int value = V; };
struct Maps { CUtensorMap ft, g32, x, u32, g64, u64, e, wr, wi, d192, d32, fg; };

constexpr int NCTA = 132;
constexpr int U = 16384;
constexpr int TB = 36864;
constexpr int NR = 5;
constexpr int OFF_RING = 8 * U, OFF_Z = 9 * U, OFF_T = 13 * U;
constexpr int OFF_BAR = 14 * U;
constexpr int SMEM_BYTES = OFF_BAR + 512;
constexpr int B_FX = 0, B_FA = 8, B_FT = 13, B_Z = 17, B_W = 21, B_HX = 22, B_HT = 23, B_HP = 24;
constexpr int B_EA = 27, B_ET = 32, B_RDY = 36;
constexpr int B_T = 37, NBAR = 38;
__host__ __device__ constexpr int rslot(int n) { return (n + 2) % NR; }
__host__ __device__ constexpr int rpar(int n) { return (n / NR) & 1; }

__global__ void __cluster_dims__(2, 1, 1) __launch_bounds__(512, 1)
fused_kernel(const __grid_constant__ Maps maps, const __nv_bfloat16* __restrict__ x, const __nv_bfloat16* __restrict__ w_r,
             const __nv_bfloat16* __restrict__ w_i, const __nv_bfloat16* __restrict__ gate_w, const __nv_bfloat16* __restrict__ Wg,
             const __nv_bfloat16* __restrict__ Wu, __nv_bfloat16* __restrict__ out) {
  extern __shared__ __align__(1024) uint8_t smem[];
  const uint32_t sb = smem_u32(smem);
  const uint32_t bars = sb + OFF_BAR;
  const int tid = threadIdx.x, lane = tid & 31;
  const int warp = __shfl_sync(0xffffffffu, tid >> 5, 0);
  const bool helper = blockIdx.x >= 128;
  const int cl = (blockIdx.x >> 1) & 63, rank = blockIdx.x & 1;
  const int q4 = cl & 3, rb = cl >> 2;
  const int j = 2 * q4 + rank;
  const int f_full = 448 * q4 + (rank ? 256 : 0);
  const int f_half = 448 * q4 + (rank ? 224 : 192);
  const int kg = 2 * j + (rb >> 3), tn = rb & 7;

  if (tid == 64) { PROF_EV(0); PROF_CK(40); }
  auto ring_part = [&](int p, int n, int slot) {
    const uint32_t fb = bars + 8 * (B_FA + slot), dst = sb + OFF_RING + slot * U;
    const bool table = n == 9 || n == 10 || n >= 34;
    const int q = n == 8 ? 0 : n - 10;
    if (p == 0) {
      mbar_expect_tx(fb, U);
      if (n < 8) tma2d(dst, &maps.ft, fb, 64 * n, 64 * j);
      else if (table) tma4d(dst, &maps.e, fb, 0, 0, 0, 2 * rb + (n >= 34 ? n - 34 : n - 9));
      else tma2d(dst, &maps.g64, fb, f_full + 64 * (q >> 3), 64 * (q & 7));
    } else if (p == 1) {
      if (n < 8) { tma2d(dst + 8192, &maps.g32, fb, f_half, 64 * n); tma2d(dst + 12288, &maps.u32, fb, f_half, 64 * n); }
      else if (!table) tma2d(dst + 8192, &maps.u64, fb, f_full + 64 * (q >> 3), 64 * (q & 7));
    }
  };
  auto x_load = [&](int q) {
    mbar_expect_tx(bars + 8 * (B_FX + q), U);
    tma3d(sb + q * U, &maps.x, bars + 8 * (B_FX + q), 64 * q, 0, 2 * rb);
  };
  if (warp < 8) {
    if (!helper) {
      const int r8 = tid >> 3, c8 = tid & 7, r4 = tid >> 2, c4 = tid & 3;
      const uint32_t sw8 = r8 * 128 + ((c8 ^ (r8 & 7)) << 4), sw4 = r4 * 64 + ((c4 ^ ((r4 >> 1) & 3)) << 4);
      const __nv_bfloat16* px = x + (size_t)(2 * rb + 32 * r8) * 512 + 8 * c8;
      const uint16_t* pf = g_FT.v + (64 * j + r8) * 512 + 8 * c8;
      const size_t om = (size_t)r4 * 1792 + f_half + 8 * c4;
#pragma unroll
      for (int kb = 0; kb < NEARLY; kb++) {
        const uint32_t dst = sb + OFF_RING + rslot(kb) * U;
#pragma unroll
        for (int i = 0; i < 4; i++) cp16(sb + kb * U + i * 4096 + sw8, px + (i & 1) * 32 * 32 * 512 + (i >> 1) * 512 + 64 * kb);
        cp16(dst + sw8, pf + 64 * kb); cp16(dst + 4096 + sw8, pf + 32 * 512 + 64 * kb);
        cp16(dst + 8192 + sw4, Wg + om + kb * 64 * 1792); cp16(dst + 12288 + sw4, Wu + om + kb * 64 * 1792);
        asm volatile("cp.async.commit_group;" ::: "memory");
      }
    }
  } else if (warp >= 12 && lane == 0) {
    asm volatile("prefetch.tensormap [%0];" ::"l"((const char*)&maps + (warp - 12) * 128) : "memory");
    if (warp == 15) {
#pragma unroll
      for (int i = B_FT; i < NBAR; i++) mbar_init(bars + 8 * i, i < B_EA ? 1 : i < B_T ? 2 : 4);
#pragma unroll
      for (int i = 0; i < 4; i++) mbar_expect_tx(bars + 8 * (B_Z + i), U);
      asm volatile("fence.mbarrier_init.release.cluster;" ::: "memory");
    } else if (warp == 14) {
#pragma unroll
      for (int i = 0; i < B_FT; i++) mbar_init(bars + 8 * i, 1);
#pragma unroll
      for (int i = 0; i < NEARLY; i++) mbar_arrive(bars + 8 * (B_FA + rslot(i)));
    } else if (warp == 13) {
#pragma unroll
      for (int i = 4; i < 12; i++) asm volatile("prefetch.tensormap [%0];" ::"l"((const char*)&maps + i * 128) : "memory");
    }
    asm volatile("fence.proxy.async.shared::cta;" ::: "memory");
  }
  __syncthreads();
  asm volatile("barrier.cluster.arrive.relaxed.aligned;" ::: "memory");
  if (tid == 64) PROF_EV(38);

  if (warp >= 12) {
    asm volatile("setmaxnreg.dec.sync.aligned.u32 24;");
    if (lane == 0 && !helper) {
      if (warp < 14) {
        int slot = rslot(NEARLY), par = 1;
#pragma unroll 1
        for (int n = NEARLY; n < 36; n++) {
          mbar_wait(bars + 8 * (B_EA + slot), par);
          ring_part(warp - 12, n, slot);
          if (++slot == NR) slot = 0;
          if (slot == rslot(0)) par ^= 1;
        }
      } else if (warp == 15) {
        const unsigned ep1 = ld_x1(&g_epoch[blockIdx.x * 8]) + 1;
        hint_wait(&g_cntX[32 * j], ep1 * 128u); mbar_arrive(bars + 8 * B_HX);
        hint_wait(&g_cntT[32 * j], ep1 * (j == 0 ? 68u : 64u)); mbar_arrive(bars + 8 * B_HT);
#pragma unroll 1
        for (int i = 0; i < 3; i++) { hint_wait(&g_cntP[32 * (rb * 8 + j) + i], ep1 * 8u); mbar_arrive(bars + 8 * (B_HP + i)); }
      } else {
#pragma unroll 1
        for (int q = NEARLY; q < 8; q++) { if (q >= NEARLY + XAHEAD) mbar_wait(bars + 8 * (B_FX + q - XAHEAD), 0); x_load(q); }
        PROF_EV(31);
#pragma unroll 1
        for (int t = 0; t < 8; t++) {
          const int i = t < 3 ? t + 1 : t < 6 ? t - 2 : 0;
          const int col = 64 * (2 * ((q4 + i) & 3) + ((t < 3 || t == 6) ? 1 - rank : rank));
          const uint32_t fb = bars + 8 * (B_FT + (t & 3)), dst = sb + (t & 3) * TB;
          mbar_wait(bars + 8 * (B_ET + (t & 3)), t >> 2);
          mbar_expect_tx(fb, TB);
          tma2d(dst, &maps.d192, fb, col, f_full);
          tma2d(dst + 24576, &maps.d32, fb, col, f_half);
          tma4d(dst + 28672, &maps.fg, fb, col, 0, 0, 4 * j);
        }
      }
    }
  } else if (warp >= 8) {
    asm volatile("setmaxnreg.dec.sync.aligned.u32 88;");
    const int t = tid - 256, w = warp - 8;
    const float scale = 2.0f / (2048.0f * 512.0f);
    const uint32_t ep = ld_x1(&g_epoch[blockIdx.x * 8]);
    const uint32_t tag = (ep + 1) & 1;
    if (!helper) {
      uint4 xv[8], gv[2];
#pragma unroll
      for (int i = 0; i < 4; i++) {
        const int r = 16 * j + 4 * w + i;
        const uint4* p = (const uint4*)(x + (size_t)(2 * rb + (r >> 6) + 32 * (r & 63)) * 512) + lane;
        xv[2 * i] = __ldg(p); xv[2 * i + 1] = __ldg(p + 32);
      }
      gv[0] = __ldg((const uint4*)gate_w + lane); gv[1] = __ldg((const uint4*)gate_w + lane + 32);
      {
        float z[4];
#pragma unroll
        for (int i = 0; i < 4; i++) {
          float a = 0.f;
#pragma unroll
          for (int hh = 0; hh < 2; hh++) {
            const uint4 u = xv[2 * i + hh], v = gv[hh];
            a = fmaf(bf_lo(u.x), bf_lo(v.x), a); a = fmaf(bf_hi(u.x), bf_hi(v.x), a);
            a = fmaf(bf_lo(u.y), bf_lo(v.y), a); a = fmaf(bf_hi(u.y), bf_hi(v.y), a);
            a = fmaf(bf_lo(u.z), bf_lo(v.z), a); a = fmaf(bf_hi(u.z), bf_hi(v.z), a);
            a = fmaf(bf_lo(u.w), bf_lo(v.w), a); a = fmaf(bf_hi(u.w), bf_hi(v.w), a);
          }
#pragma unroll
          for (int o = 16; o; o >>= 1) a += __shfl_xor_sync(0xffffffffu, a, o);
          z[i] = a;
        }
        if (lane < 4) {
          const float zz = lane == 0 ? z[0] : lane == 1 ? z[1] : lane == 2 ? z[2] : z[3];
          asm volatile("st.relaxed.gpu.global.f32 [%0], %1;" ::"l"(g_gate + rb * 128 + 16 * j + 4 * w + lane), "f"(tagf(1.0f / (1.0f + __expf(-zz)), tag)) : "memory");
        }
        if (t == 0) PROF_EV(18);
      }
      if (w == 0) {
        const int c = lane >> 4, jj = 16 * blockIdx.x + (lane & 15), jm = (2048 - jj) & 2047;
        const unsigned short* pr = (const unsigned short*)w_r + 256 * c;
        const unsigned short* pi = (const unsigned short*)w_i + 256 * c;
        const float wr = 0.5f * (bf_lo(__ldg(pr + jj * 257)) + bf_lo(__ldg(pr + jm * 257)));
        const float wi = 0.5f * (bf_lo(__ldg(pi + jj * 257)) - bf_lo(__ldg(pi + jm * 257)));
        st_u2(g_Wh + c * 2048 + jj, c ? pack_bf16(-wi, wr) : pack_bf16(wr, wi), tag);
        __syncwarp();
        if (lane == 0) hint_add(&g_cntW[0]);
      }
    }
    if (!helper || w == 0) {
      const int hc = lane >> 4, hj = 16 * (blockIdx.x - 128) + (lane & 15);
      uint32_t u[32];
      if (!helper) {
        const unsigned short* p = (const unsigned short*)(smem + OFF_T) + (t >> 4) * 25 + (t & 15);
#pragma unroll 1
        for (int ri = 0; ri < 2; ri++) {
          if (t == 32) {
            if (ri == 0) { mbar_wait(bars + 8 * (B_FX + WAFTER), 0); PROF_EV(32); }
            mbar_expect_tx(bars + 8 * B_W, 12288);
#pragma unroll 1
            for (int i = 0; i < 4; i++) { tma4d(sb + OFF_T + i * 3072, ri ? &maps.wi : &maps.wr, bars + 8 * B_W, 16 * kg, 0, tn, 8 * i); __nanosleep(WPACE); }
          }
          mbar_wait(bars + 8 * B_W, ri);
#pragma unroll
          for (int a = 0; a < 32; a++) u[a] = __byte_perm(u[a], p[a * 192], 0x5432);
          asm volatile("bar.sync 1, 128;" ::: "memory");
        }
      } else {
        hint_wait(&g_cntW[0], (ep + 1) * 128u);
        const uint32_t t0 = (uint32_t)clock();
#pragma unroll 1
        for (;;) {
          uint32_t bad = 0;
#pragma unroll
          for (int a = 0; a < 32; a++) { const float2 v = ld_x2((const float2*)g_Wh + hc * 2048 + hj + 64 * a); u[a] = __float_as_uint(v.x); bad |= __float_as_uint(v.y) ^ tag; }
          if (!__any_sync(0xffffffffu, bad & 1)) break;
          spin_guard(t0);
        }
      }
#pragma unroll
      for (int a = 0; a < 8; a++) *(uint4*)(smem + OFF_T + (a * 128 + t) * 16) = make_uint4(u[4 * a], u[4 * a + 1], u[4 * a + 2], u[4 * a + 3]);
      if (t == 0) PROF_EV(11);
      if (helper) hint_wait(&g_cntX[0], (ep + 1) * 128u); else mbar_wait(bars + 8 * B_HX, 0);
      if (t == 0) PROF_EV(22);
      float2 v[32];
      {
        const int odd = helper ? (lane & 1) : ((t >> 4) & 1);
        const uint32_t* src = (const uint32_t*)(helper ? g_X1s + hc * 32 + (hj >> 1) : g_X1p + (size_t)(kg * 8 + tn) * 2048 + ((t >> 3) & 1) * 32 + w * 8 + (t & 7)) + odd;
        const uint32_t chk = odd ^ 1;
        const uint32_t t0 = (uint32_t)clock();
#pragma unroll 1
        for (;;) {
          uint32_t bad = 0;
#pragma unroll
          for (int a = 0; a < 32; a++) u[a] = ld_x1(src + a * 128);
#pragma unroll
          for (int a = 0; a < 32; a++) bad |= u[a] ^ tag;
          if (!__any_sync(0xffffffffu, bad & chk)) break;
          spin_guard(t0);
        }
#pragma unroll
        for (int a = 0; a < 32; a++) v[a] = make_float2(bf_lo(u[a] & ~chk), bf_hi(u[a]));
      }
      if (t == 0) PROF_EV(12);
#pragma unroll 1
      for (int pass = 0;; pass++) {
        dft<-1, 32, 0, 1>(v);
        if (pass) break;
        float2 y[32];
#pragma unroll
        for (int a4 = 0; a4 < 8; a4++) {
          const uint4 ww = *(const uint4*)(smem + OFF_T + (a4 * 128 + t) * 16);
          const uint32_t wq[4] = {ww.x, ww.y, ww.z, ww.w};
#pragma unroll
          for (int e = 0; e < 4; e++) {
            const float2 z = v[brev(4 * a4 + e, 5)];
            const float wr = bf_lo(wq[e]), wi = bf_hi(wq[e]);
            y[4 * a4 + e] = make_float2(fmaf(z.x, wi, z.y * wr), fmaf(z.x, wr, -z.y * wi));
          }
        }
#pragma unroll
        for (int a = 0; a < 32; a++) v[a] = y[a];
      }
      if (t == 0) PROF_EV(16);
      if (!helper) {
        uint2* dst = g_T + (size_t)j * 32768 + (kg & 1) * 1024 + (8 * tn + (t >> 4)) * 16 + (t & 15);
        const bool real_col = kg == 0 && (t & 15) == 0;
#pragma unroll
        for (int a = 0; a < 16; a++) {
          const float2 u0 = v[brev(2 * a, 5)], u1 = v[brev(2 * a + 1, 5)];
          if (!real_col) st_u2(dst + a * 2048, (pack_bf16(u0.y * scale, u0.x * scale) & ~1u) | tag, pack_bf16(u1.y * scale, u1.x * scale));
          if (TPACE && (a & 3) == 3 && a < 15) __nanosleep(TPACE);
        }
        __syncwarp();
        if (lane == 0) hint_add(&g_cntT[32 * j]);
        if (t == 0) PROF_EV(17);
        const uint4* src = (const uint4*)(g_T + (size_t)(j * 16 + rb) * 2048) + t;
        uint4 tv[8];
        mbar_wait(bars + 8 * B_HT, 0);
        if (t == 0) PROF_EV(23);
        const uint32_t t0 = (uint32_t)clock();
#pragma unroll 1
        for (;;) {
          uint32_t bad = 0;
#pragma unroll
          for (int a = 0; a < 8; a++) tv[a] = ld_x4(src + a * 128);
#pragma unroll
          for (int a = 0; a < 8; a++) bad |= (tv[a].x ^ tag) | (tv[a].z ^ tag);
          if (!__any_sync(0xffffffffu, bad & 1)) break;
          spin_guard(t0);
        }
        const int r = t >> 3, c = t & 7;
#pragma unroll
        for (int a = 0; a < 8; a++) {
          const uint32_t dst2 = sb + OFF_T + (16 * (a & 3) + r) * 128 + ((((a >> 2) * 4 + (c >> 1)) ^ (r & 7)) << 4) + (c & 1) * 8;
          asm volatile("st.shared.v2.u32 [%0], {%1,%2};" ::"r"(dst2), "r"(tv[a].x & ~1u), "r"(tv[a].z & ~1u) : "memory");
          asm volatile("st.shared.v2.u32 [%0], {%1,%2};" ::"r"(dst2 + 8192), "r"(tv[a].y), "r"(tv[a].w) : "memory");
        }
        asm volatile("fence.proxy.async.shared::cta;" ::: "memory");
        __syncwarp();
        if (lane == 0) mbar_arrive(bars + 8 * B_T);
        if (t == 0) PROF_EV(13);
      } else {
#pragma unroll
        for (int a = 0; a < 8; a++) {
          uint32_t pk[2];
#pragma unroll
          for (int e = 0; e < 2; e++) {
            const float2 u0 = v[brev(4 * a + e, 5)], u1 = v[brev(4 * a + 2 + e, 5)];
            const float2 keep = hc ? u1 : u0, give = hc ? u0 : u1;
            const float ox = __shfl_xor_sync(0xffffffffu, give.x, 16), oy = __shfl_xor_sync(0xffffffffu, give.y, 16);
            pk[e] = pack_bf16((keep.y + oy) * (0.5f * scale), (keep.x + ox) * (0.5f * scale));
          }
          st_u2(g_T + (2 * a + hc) * 2048 + hj * 16, (pk[0] & ~1u) | tag, pk[1]);
        }
        __syncwarp();
        if (t == 0) { hint_add(&g_cntT[0]); g_epoch[blockIdx.x * 8] = ep + 1; PROF_EV(13); }
      }
    }
  } else {
    asm volatile("setmaxnreg.inc.sync.aligned.u32 200;");
    if (!helper) {
      const int wg = warp >> 2, w = warp & 3, g = lane >> 2, q = lane & 3;
      const bool elect = (tid & 127) == 0;
      const uint32_t ep = ld_x1(&g_epoch[blockIdx.x * 8]);
      float c1[64], cA[64], c2[64], ci[64], ct[64];
      const int zero = blockIdx.x >> 16;
      uint32_t h[56], yf[16];
      const uint32_t d0 = (sb & 0x3FFFF) >> 4;
      const uint32_t dK = d0 | (1u << 16), dN = d0 | (512u << 16), dM = d0 | (256u << 16);
      const uint32_t dX = dK + wg * 512;
      constexpr uint32_t RING = OFF_RING >> 4;
      auto waitA = [&](int n) { mbar_wait(bars + 8 * (B_FA + rslot(n)), rpar(n)); };
      auto freeA = [&](int n) { if (elect) mbar_arrive(bars + 8 * (B_EA + rslot(n))); };
      auto nop = [](int) {};

#pragma unroll
      for (int kb = 0; kb < 8; kb++) {
        if (kb < NEARLY) {
          if (NEARLY - 1 - kb == 3) asm volatile("cp.async.wait_group 3;" ::: "memory");
          else if (NEARLY - 1 - kb == 2) asm volatile("cp.async.wait_group 2;" ::: "memory");
          else if (NEARLY - 1 - kb == 1) asm volatile("cp.async.wait_group 1;" ::: "memory");
          else asm volatile("cp.async.wait_group 0;" ::: "memory");
          asm volatile("fence.proxy.async.shared::cta;" ::: "memory");
          asm volatile("bar.sync 2, 256;" ::: "memory");
        } else {
          mbar_wait(bars + 8 * (B_FX + kb), 0); waitA(kb);
        }
        wg_fence();
        const uint64_t dx = d128(dX + kb * 1024), df = d128(dK + RING + rslot(kb) * 1024), dm = d64(dM + RING + 512 + rslot(kb) * 1024);
        if (kb == 0) { mma_ss64<0, 0, 0>(c1, df, dx); mma_ss64<32, 1, 0>(c1, dx, dm); }
        else { mma_ss64<0, 0, 1>(c1, df, dx); mma_ss64<32, 1, 1>(c1, dx, dm); wg_commit(); wg_wait<1>(); freeA(kb - 1); }
#pragma unroll
        for (int k = 1; k < 4; k++) {
          mma_ss64<0, 0, 1>(c1, df + k * 2, dx + k * 2);
          mma_ss64<32, 1, 1>(c1, dx + k * 2, dm + k * 64);
        }
        wg_commit();
        if (kb == 0 && tid == 0) PROF_EV(1);
      }
      auto ffn_step = [&](auto first, float (&acc)[64], int n, int kb, auto done, auto work) {
        waitA(n);
        wg_fence();
        const uint64_t dx = d128(dX + kb * 1024), db = d128(dN + RING + rslot(n) * 1024);
        mma_ss128<0, 1, decltype(first)::value>(acc, dx, db, zero);
        wg_commit();
        wg_wait<1>();
        done();
#pragma unroll
        for (int k = 1; k < 4; k++) { mma_ss128<0, 1, 1>(acc, dx + k * 2, db + k * 128); work(k - 1); }
        wg_commit();
        work(3);
      };
      const uint32_t tag = (ep + 1) & 1;
      float hm[16];
      ffn_step(IC<0>(), c2, 8, 0, [&] { freeA(7); fence_regs<0, 64>(c1); }, [&](int i) {
#pragma unroll
        for (int e = 4 * i; e < 4 * i + 4; e++) { yf[e] = pack_pin(c1[2 * e], c1[2 * e + 1]); hm[e] = fmaxf(c1[32 + e], 0.f) * c1[48 + e]; }
      });
      fence_regs<0, 16>(hm);
      if (tid == 0) PROF_EV(2);
      {
        waitA(9); waitA(10);
        const uint64_t de = d128(dN + RING + (wg ? rslot(10) : rslot(9)) * 1024);
        wg_fence();
        mma_rs128<0, 1, 0>(cA, yf[0], yf[1], yf[2], yf[3], de);
        wg_commit();
        wg_wait<1>();
        freeA(8);
#pragma unroll
        for (int k = 1; k < 4; k++) mma_rs128<0, 1, 1>(cA, yf[4 * k], yf[4 * k + 1], yf[4 * k + 2], yf[4 * k + 3], de + k * 128);
        wg_commit();
      }
      {
        const int s0 = 2 * rb + wg;
        uint2* dst = g_X1p + ((size_t)((2 * j + (w >> 1)) * 8) * 32 + s0) * 64 + (w & 1) * 32 + q * 8 + g;
        auto x1_store = [&](int n) {
          st_u2(dst + n * 2048, (pack_bf16(cA[4 * n] - cA[34 + 4 * n], cA[32 + 4 * n] + cA[4 * n + 2]) & ~1u) | tag,
                pack_bf16(cA[4 * n + 1] - cA[35 + 4 * n], cA[33 + 4 * n] + cA[4 * n + 3]));
        };
        ffn_step(IC<1>(), c2, 11, 1, [&] { freeA(9); freeA(10); fence_regs<0, 64>(cA); }, [&](int i) { x1_store(i); });
        if (tid == 0) PROF_EV(19);
        ffn_step(IC<1>(), c2, 12, 2, [&] { freeA(11); }, [&](int i) { x1_store(4 + i); });
        if (j == 0 && w == 0 && g == 0) {
#pragma unroll
          for (int n = 0; n < 8; n++) {
            st_u2(g_X1s + s0 * 64 + 4 * n + q, (pack_bf16(cA[4 * n], cA[32 + 4 * n]) & ~1u) | tag, pack_bf16(cA[4 * n + 1], cA[33 + 4 * n]));
            st_u2(g_X1s + s0 * 64 + 32 + 4 * n + q, (pack_bf16(cA[4 * n + 2], cA[34 + 4 * n]) & ~1u) | tag, pack_bf16(cA[4 * n + 3], cA[35 + 4 * n]));
          }
        }
        __syncwarp();
        if (lane == 0) hint_add(&g_cntX[32 * j]);
        if (tid == 0) PROF_EV(3);
      }
      const float* gp = g_gate + rb * 128 + wg * 64 + w * 16 + g;
      uint32_t gb0 = ld_x1(gp), gb1 = ld_x1(gp + 8);
#pragma unroll
      for (int kb = 3; kb < 7; kb++) ffn_step(IC<1>(), c2, 10 + kb, kb, [&] { freeA(9 + kb); }, nop);
      {
        const uint32_t t0 = (uint32_t)clock();
        while (__any_sync(0xffffffffu, ((gb0 ^ tag) | (gb1 ^ tag)) & 1)) { gb0 = ld_x1(gp); gb1 = ld_x1(gp + 8); spin_guard(t0); }
      }
      const float g0 = __uint_as_float(gb0 & ~1u), g1 = __uint_as_float(gb1 & ~1u);
      const float o0 = 1.0f - g0, o1 = 1.0f - g1;
      ffn_step(IC<1>(), c2, 17, 7, [&] { freeA(16); }, [&](int i) {
        h[48 + 2 * i] = pack_pin(hm[4 * i] * o0, hm[4 * i + 1] * o0); h[49 + 2 * i] = pack_pin(hm[4 * i + 2] * o1, hm[4 * i + 3] * o1);
      });
      auto glu = [&](float (&acc)[64], int ho, int i0, int i1) {
#pragma unroll
        for (int i = i0; i < i1; i++) {
          const float o = (i & 1) ? o1 : o0;
          h[ho + i] = pack_pin(fmaxf(acc[2 * i], 0.f) * acc[32 + 2 * i] * o, fmaxf(acc[2 * i + 1], 0.f) * acc[33 + 2 * i] * o);
        }
      };
      ffn_step(IC<2>(), cA, 18, 0, [&] { freeA(17); fence_regs<0, 64>(c2); }, [&](int i) { glu(c2, 0, 2 * i, 2 * i + 2); });
      if (tid == 0) PROF_EV(4);
      ffn_step(IC<1>(), cA, 19, 1, [&] { freeA(18); }, [&](int i) { glu(c2, 0, 8 + 2 * i, 10 + 2 * i); });
#pragma unroll
      for (int kb = 2; kb < 8; kb++) ffn_step(IC<1>(), cA, 18 + kb, kb, [&] { freeA(17 + kb); }, nop);
      ffn_step(IC<2>(), c2, 26, 0, [&] { freeA(25); fence_regs<0, 64>(cA); }, [&](int i) { glu(cA, 16, 2 * i, 2 * i + 2); });
      if (tid == 0) PROF_EV(5);
      ffn_step(IC<1>(), c2, 27, 1, [&] { freeA(26); }, [&](int i) { glu(cA, 16, 8 + 2 * i, 10 + 2 * i); });
#pragma unroll
      for (int kb = 2; kb < 8; kb++)
        ffn_step(IC<1>(), c2, 26 + kb, kb, [&] {
          if (kb < 6) freeA(25 + kb);
          if (kb >= 3 && (kb & 1) && elect) mbar_arrive(bars + 8 * (B_ET + ((kb - 3) >> 1)));
        }, nop);
      wg_wait<0>();
      if (elect) mbar_arrive(bars + 8 * (B_ET + 3));
      fence_regs<0, 64>(c2);
      glu(c2, 32, 0, 16);
      if (wg) waitA(35); else waitA(34);
      if (tid == 0) PROF_EV(6);
      mbar_wait(bars + 8 * B_T, 0);
      if (tid == 0) PROF_EV(7);
      wg_fence();
      {
        const uint64_t dt = d128(dN + (OFF_T >> 4) + wg * 512), de = d128(dK + RING + (wg ? rslot(35) : rslot(34)) * 1024);
        mma_ss64<0, 1, 0>(ci, de, dt);
        mma_ss64<32, 1, 0>(ci, de + 512, dt);
#pragma unroll
        for (int k = 1; k < 4; k++) {
          mma_ss64<0, 1, 1>(ci, de + k * 2, dt + k * 128);
          mma_ss64<32, 1, 1>(ci, de + (512 + k * 2), dt + k * 128);
        }
      }
      wg_commit();

      auto head = [&](auto off, int t) {
        constexpr int O = decltype(off)::value;
        mbar_wait(bars + 8 * (B_FT + (t & 3)), t >> 2);
        const uint64_t db = d128(dN + (t & 3) * (TB >> 4));
        wg_fence();
        mma_rs64<O, 1, 0>(ct, h[0], h[1], h[2], h[3], db);
#pragma unroll
        for (int k = 1; k < 6; k++) mma_rs64<O, 1, 1>(ct, h[4 * k], h[4 * k + 1], h[4 * k + 2], h[4 * k + 3], db + k * 128);
        wg_commit();
        wg_wait<1>();
      };
      auto rest = [&](auto off, int t) {
        constexpr int O = decltype(off)::value;
        const uint64_t db = d128(dN + (t & 3) * (TB >> 4));
        wg_fence();
#pragma unroll
        for (int k = 6; k < 14; k++) mma_rs64<O, 1, 1>(ct, h[4 * k], h[4 * k + 1], h[4 * k + 2], h[4 * k + 3], db + k * 128);
#pragma unroll
        for (int k = 0; k < 4; k++) mma_rs64<O, 1, 1>(ct, yf[4 * k], yf[4 * k + 1], yf[4 * k + 2], yf[4 * k + 3], db + (14 + k) * 128);
        wg_commit();
      };
      auto freeT = [&](int t) { if (elect) mbar_arrive(bars + 8 * (B_ET + t)); };
      const uint32_t peerZ = mapa(sb + OFF_Z + tid * 16, rank ^ 1), peerB = mapa(bars + 8 * B_Z, rank ^ 1);
      auto send_peer = [&](auto off, int z) {
        constexpr int O = decltype(off)::value;
        fence_regs<O, 32>(ct);
#pragma unroll
        for (int i = 0; i < 4; i++)
          asm volatile("st.async.weak.shared::cluster.mbarrier::complete_tx::bytes.v4.b32 [%0], {%1,%2,%3,%4}, [%5];" ::"r"(peerZ + z * U + i * 4096),
                       "r"(pack_bf16(ct[O + 8 * i], ct[O + 8 * i + 1])), "r"(pack_bf16(ct[O + 8 * i + 2], ct[O + 8 * i + 3])),
                       "r"(pack_bf16(ct[O + 8 * i + 4], ct[O + 8 * i + 5])), "r"(pack_bf16(ct[O + 8 * i + 6], ct[O + 8 * i + 7])), "r"(peerB + 8 * z) : "memory");
      };
      auto send_grid = [&](auto off, int z) {
        constexpr int O = decltype(off)::value;
        fence_regs<O, 32>(ct);
        mbar_wait(bars + 8 * (B_Z + z), 0);
        uint4* dst = g_part + (size_t)((rb * 8 + 2 * ((q4 + z + 1) & 3) + rank) * 3 + z) * 1024 + tid;
#pragma unroll
        for (int i = 0; i < 4; i++) {
          const uint4 p = *(const uint4*)(smem + OFF_Z + z * U + i * 4096 + tid * 16);
          st_x4(dst + i * 256, (pack_bf16(ct[O + 8 * i] + bf_lo(p.x), ct[O + 8 * i + 1] + bf_hi(p.x)) & ~1u) | tag,
                pack_bf16(ct[O + 8 * i + 2] + bf_lo(p.y), ct[O + 8 * i + 3] + bf_hi(p.y)),
                pack_bf16(ct[O + 8 * i + 4] + bf_lo(p.z), ct[O + 8 * i + 5] + bf_hi(p.z)),
                pack_bf16(ct[O + 8 * i + 6] + bf_lo(p.w), ct[O + 8 * i + 7] + bf_hi(p.w)));
        }
        __syncwarp();
        if (lane == 0) hint_add(&g_cntP[32 * (rb * 8 + 2 * ((q4 + z + 1) & 3) + rank) + z]);
      };
      asm volatile("barrier.cluster.wait.aligned;" ::: "memory");
      head(IC<0>(), 0);
      if (elect) asm volatile("mbarrier.arrive.shared::cluster.b64 _, [%0];" ::"r"(mapa(bars + 8 * B_RDY, rank ^ 1)) : "memory");
      fence_regs<0, 64>(ci);
#pragma unroll
      for (int i = 0; i < 16; i++) {
        const float gg = (i & 1) ? g1 : g0;
        yf[i] = pack_pin((ci[2 * i] + ci[33 + 2 * i]) * gg, (ci[2 * i + 1] - ci[32 + 2 * i]) * gg);
      }
      rest(IC<0>(), 0);
      if (tid == 0) PROF_EV(8);
      head(IC<32>(), 1); freeT(0); mbar_wait(bars + 8 * B_RDY, 0); send_peer(IC<0>(), 0); rest(IC<32>(), 1);
      head(IC<0>(), 2); freeT(1); send_peer(IC<32>(), 1); rest(IC<0>(), 2);
      head(IC<32>(), 3); freeT(2); send_peer(IC<0>(), 2); rest(IC<32>(), 3);
      head(IC<0>(), 4); freeT(3); send_grid(IC<32>(), 0); rest(IC<0>(), 4);
      head(IC<32>(), 5); send_grid(IC<0>(), 1); rest(IC<32>(), 5);
      head(IC<0>(), 6); send_grid(IC<32>(), 2); rest(IC<0>(), 6);
      head(IC<32>(), 7); send_peer(IC<0>(), 3);
      {
        const uint4* src = g_part + (size_t)(rb * 8 + j) * 3 * 1024 + tid;
        uint4 pv[12];
        mbar_wait(bars + 8 * (B_HP + 1), 0);
#pragma unroll
        for (int i = 0; i < 8; i++) pv[i] = ld_x4(src + i * 256);
        rest(IC<32>(), 7);
        if (tid == 0) PROF_EV(9);
        mbar_wait(bars + 8 * (B_HP + 2), 0);
        if (tid == 0) PROF_EV(24);
#pragma unroll
        for (int i = 8; i < 12; i++) pv[i] = ld_x4(src + i * 256);
        const uint32_t t0 = (uint32_t)clock();
        for (;;) {
          uint32_t bad = 0;
#pragma unroll
          for (int i = 0; i < 12; i++) bad |= pv[i].x ^ tag;
          if (!__any_sync(0xffffffffu, bad & 1)) break;
#pragma unroll
          for (int i = 0; i < 12; i++) pv[i] = ld_x4(src + i * 256);
          spin_guard(t0);
        }
        if (tid == 0) PROF_EV(14);
        float sum[32];
#pragma unroll
        for (int i = 0; i < 4; i++) {
          const uint32_t a[4] = {pv[i].x & ~1u, pv[i].y, pv[i].z, pv[i].w}, b[4] = {pv[4 + i].x & ~1u, pv[4 + i].y, pv[4 + i].z, pv[4 + i].w},
                         c[4] = {pv[8 + i].x & ~1u, pv[8 + i].y, pv[8 + i].z, pv[8 + i].w};
#pragma unroll
          for (int e = 0; e < 4; e++) {
            sum[8 * i + 2 * e] = bf_lo(a[e]) + bf_lo(b[e]) + bf_lo(c[e]);
            sum[8 * i + 2 * e + 1] = bf_hi(a[e]) + bf_hi(b[e]) + bf_hi(c[e]);
          }
        }
        mbar_wait(bars + 8 * (B_Z + 3), 0);
#pragma unroll
        for (int i = 0; i < 4; i++) {
          const uint4 p = *(const uint4*)(smem + OFF_Z + 3 * U + i * 4096 + tid * 16);
          const uint32_t a[4] = {p.x, p.y, p.z, p.w};
#pragma unroll
          for (int e = 0; e < 4; e++) { sum[8 * i + 2 * e] += bf_lo(a[e]); sum[8 * i + 2 * e + 1] += bf_hi(a[e]); }
        }
        wg_wait<0>();
        fence_regs<32, 32>(ct);
#pragma unroll
        for (int i = 0; i < 32; i++) sum[i] += ct[32 + i];
        const uint32_t stg = sb + OFF_T + warp * 2048;
        const int mr = (lane & 7) + ((lane >> 3) & 1) * 8, mc = lane >> 4;
#pragma unroll
        for (int i = 0; i < 4; i++) {
          const uint32_t a = stg + mr * 128 + (((2 * i + mc) ^ (mr & 7)) << 4);
          asm volatile("stmatrix.sync.aligned.m8n8.x4.shared.b16 [%0], {%1,%2,%3,%4};" ::"r"(a), "r"(pack_bf16(sum[8 * i], sum[8 * i + 1])),
                       "r"(pack_bf16(sum[8 * i + 2], sum[8 * i + 3])), "r"(pack_bf16(sum[8 * i + 4], sum[8 * i + 5])),
                       "r"(pack_bf16(sum[8 * i + 6], sum[8 * i + 7])) : "memory");
        }
        __syncwarp();
#pragma unroll
        for (int i = 0; i < 4; i++) {
          const int r = 4 * i + (lane >> 3), c = lane & 7;
          const uint4 v = *(const uint4*)(smem + OFF_T + warp * 2048 + r * 128 + ((c ^ (r & 7)) << 4));
          *(uint4*)(out + (size_t)(2 * rb + wg + 32 * (16 * w + r)) * 512 + 64 * j + 8 * c) = v;
        }
      }
      if (tid == 0) { g_epoch[blockIdx.x * 8] = ep + 1; PROF_EV(15); PROF_CK(41); }
    }
  }
}

typedef CUresult (*EncodeFn)(CUtensorMap*, CUtensorMapDataType, cuuint32_t, void*, const cuuint64_t*, const cuuint64_t*, const cuuint32_t*,
                             const cuuint32_t*, CUtensorMapInterleave, CUtensorMapSwizzle, CUtensorMapL2promotion, CUtensorMapFloatOOBfill);

static void encode(EncodeFn f, CUtensorMap* m, const void* base, int rank, const cuuint64_t* dims, const cuuint64_t* strides, const cuuint32_t* box,
                   CUtensorMapSwizzle sw) {
  cuuint32_t es[5] = {1, 1, 1, 1, 1};
  f(m, CU_TENSOR_MAP_DATA_TYPE_BFLOAT16, rank, (void*)base, dims, strides, box, es, CU_TENSOR_MAP_INTERLEAVE_NONE, sw,
    CU_TENSOR_MAP_L2_PROMOTION_L2_128B, CU_TENSOR_MAP_FLOAT_OOB_FILL_NONE);
}

extern "C" void kernel_launch(void* const* d_in, const int* in_sizes, int n_in, void* d_out, int out_size) {
  (void)in_sizes; (void)n_in; (void)out_size;
  const __nv_bfloat16* x = (const __nv_bfloat16*)d_in[0];
  const __nv_bfloat16* w_r = (const __nv_bfloat16*)d_in[1];
  const __nv_bfloat16* w_i = (const __nv_bfloat16*)d_in[2];
  const __nv_bfloat16* Wg = (const __nv_bfloat16*)d_in[4];
  const __nv_bfloat16* Wu = (const __nv_bfloat16*)d_in[5];
  const __nv_bfloat16* Wd = (const __nv_bfloat16*)d_in[6];
  const __nv_bfloat16* gw = (const __nv_bfloat16*)d_in[7];

  void* fp = nullptr; cudaDriverEntryPointQueryResult qr;
  cudaGetDriverEntryPoint("cuTensorMapEncodeTiled", &fp, cudaEnableDefault, &qr);
  EncodeFn enc = (EncodeFn)fp;
  void *pFT, *pET;
  cudaGetSymbolAddress(&pFT, g_FT); cudaGetSymbolAddress(&pET, g_ET);

  Maps mp;
  const CUtensorMapSwizzle S128 = CU_TENSOR_MAP_SWIZZLE_128B, S64 = CU_TENSOR_MAP_SWIZZLE_64B;
  { cuuint64_t d[3] = {512, 64, 32}, s[2] = {32768, 1024}; cuuint32_t b[3] = {64, 64, 2}; encode(enc, &mp.x, x, 3, d, s, b, S128); }
  { cuuint64_t d[2] = {512, 512}, s[1] = {1024}; cuuint32_t b[2] = {64, 64}; encode(enc, &mp.ft, pFT, 2, d, s, b, S128); }
  { cuuint64_t d[4] = {512, 2, 8, 32}, s[3] = {8192, 1024, 16384}; cuuint32_t b[4] = {64, 2, 8, 4}; encode(enc, &mp.fg, pFT, 4, d, s, b, S128); }
  { cuuint64_t d[4] = {64, 64, 2, 32}, s[3] = {8192, 128, 256}; cuuint32_t b[4] = {64, 64, 2, 1}; encode(enc, &mp.e, pET, 4, d, s, b, S128); }
  { cuuint64_t d[2] = {1792, 512}, s[1] = {3584}; cuuint32_t b[2] = {64, 64}, b2[2] = {32, 64};
    encode(enc, &mp.g64, Wg, 2, d, s, b, S128); encode(enc, &mp.u64, Wu, 2, d, s, b, S128);
    encode(enc, &mp.g32, Wg, 2, d, s, b2, S64); encode(enc, &mp.u32, Wu, 2, d, s, b2, S64); }
  { cuuint64_t d[2] = {512, 1792}, s[1] = {1024}; cuuint32_t b[2] = {64, 192}, b2[2] = {64, 32};
    encode(enc, &mp.d192, Wd, 2, d, s, b, S128); encode(enc, &mp.d32, Wd, 2, d, s, b2, S128); }

  { cuuint64_t d[4] = {264, 8, 8, 32}, s[3] = {512, 4112, 32896}; cuuint32_t b[4] = {24, 8, 1, 8};
    encode(enc, &mp.wr, w_r, 4, d, s, b, CU_TENSOR_MAP_SWIZZLE_NONE); encode(enc, &mp.wi, w_i, 4, d, s, b, CU_TENSOR_MAP_SWIZZLE_NONE); }

  cudaFuncSetAttribute(fused_kernel, cudaFuncAttributeMaxDynamicSharedMemorySize, SMEM_BYTES);
  fused_kernel<<<NCTA, 512, SMEM_BYTES>>>(mp, x, w_r, w_i, gw, Wg, Wu, (__nv_bfloat16*)d_out);
}
```

```cpp
#include <cuda_runtime.h>
#include <cuda_bf16.h>
#include <cuda.h>
#include <stdint.h>

namespace tbl {
constexpr double PI = 3.14159265358979323846264338327950288;
constexpr double sin_s(double x) { double t = x, s = x; for (int n = 1; n < 12; n++) { t *= -x * x / ((2 * n) * (2 * n + 1)); s += t; } return s; }
constexpr double cos_s(double x) { double t = 1, s = 1; for (int n = 1; n < 12; n++) { t *= -x * x / ((2 * n - 1) * (2 * n)); s += t; } return s; }
constexpr double cos2048(int m) {
  m &= 2047; if (m > 1024) m = 2048 - m;
  bool neg = false; if (m > 512) { m = 1024 - m; neg = true; }
  double v = (m <= 256) ? cos_s(2 * PI * m / 2048) : sin_s(2 * PI * (512 - m) / 2048);
  return neg ? -v : v;
}
constexpr uint16_t to_bf16(double v) {
  if (v == 0) return 0;
  uint16_t s = 0; if (v < 0) { s = 0x8000; v = -v; }
  int e = 0; while (v >= 2) { v /= 2; e++; } while (v < 1) { v *= 2; e--; }
  double m = (v - 1) * 128; int mi = (int)m; double fr = m - mi;
  if (fr > 0.5 || (fr == 0.5 && (mi & 1))) mi++;
  if (mi == 128) { mi = 0; e++; }
  return (uint16_t)(s | ((e + 127) << 7) | mi);
}
struct CosT { uint16_t v[2048]; constexpr CosT() : v() { for (int i = 0; i < 2048; i++) v[i] = to_bf16(cos2048(i)); } };
struct alignas(1024) FT {
  uint16_t v[512 * 512];
  constexpr FT() : v() {
    CosT c;
    for (int r = 0; r < 512; r++) {
      int k = (r >> 4) * 8 + (r & 7), e = (r >> 3) & 1;
      int mul = 4 * k, add = e ? 512 : 0;
      if (k == 0 && e == 1) { mul = 1024; add = 0; }
      for (int d = 0; d < 512; d++) v[r * 512 + d] = c.v[(d * mul + add) & 2047];
    }
  }
};
struct alignas(1024) ET {
  uint16_t v[2048 * 128];
  constexpr ET() : v() {
    CosT c;
    for (int s = 0; s < 2048; s++)
      for (int j = 0; j < 64; j++) { v[s * 128 + j] = c.v[(s * j) & 2047]; v[s * 128 + 64 + j] = c.v[(s * j + 512) & 2047]; }
  }
};
template <int A> struct W32 {
  static constexpr float c = (float)cos2048(A * 64);
  static constexpr float s = (float)cos2048(A * 64 - 512);
};
}

__device__ constexpr tbl::FT g_FT = tbl::FT();
__device__ constexpr tbl::ET g_ET = tbl::ET();

__device__ __align__(1024) uint2 g_X1p[128 * 32 * 64];
__device__ __align__(1024) uint2 g_X1s[32 * 64];
__device__ __align__(1024) uint2 g_T[8 * 16 * 2 * 64 * 16];
__device__ __align__(1024) uint4 g_part[128 * 3 * 1024];
__device__ __align__(16) float g_gate[16 * 128];
__device__ __align__(16) uint2 g_Wh[2 * 2048];
__device__ unsigned g_epoch[132 * 8];
__device__ unsigned g_cntX[8 * 32], g_cntT[8 * 32], g_cntP[128 * 32], g_cntW[32];
#define PROF_EV(i) do {} while (0)
#define PROF_CK(i) do {} while (0)

__device__ __forceinline__ uint32_t smem_u32(const void* p) { return (uint32_t)__cvta_generic_to_shared(p); }
__device__ __forceinline__ void mbar_init(uint32_t bar, uint32_t cnt) { asm volatile("mbarrier.init.shared::cta.b64 [%0], %1;" ::"r"(bar), "r"(cnt)); }
__device__ __forceinline__ void mbar_expect_tx(uint32_t bar, uint32_t bytes) { asm volatile("mbarrier.arrive.expect_tx.shared::cta.b64 _, [%0], %1;" ::"r"(bar), "r"(bytes) : "memory"); }
__device__ __forceinline__ void mbar_arrive(uint32_t bar) { asm volatile("mbarrier.arrive.shared::cta.b64 _, [%0];" ::"r"(bar) : "memory"); }
__device__ __forceinline__ void mbar_wait(uint32_t bar, uint32_t parity) {
  asm volatile(
      "{\n.reg .pred p;\n.reg .u32 n;\nmov.u32 n, 0;\n"
      "W_LOOP:\nmbarrier.try_wait.parity.shared::cta.b64 p, [%0], %1;\n@p bra W_DONE;\n"
      "add.u32 n, n, 1;\nsetp.lt.u32 p, n, 0x40000;\n@p bra W_LOOP;\ntrap;\nW_DONE:\n}" ::"r"(bar), "r"(parity) : "memory");
}
__device__ __forceinline__ void cp16(uint32_t dst, const void* src) { asm volatile("cp.async.cg.shared.global [%0], [%1], 16;" ::"r"(dst), "l"(src) : "memory"); }
__device__ __forceinline__ void spin_guard(uint32_t t0) { if ((uint32_t)clock() - t0 > (1u << 30)) __trap(); }
__device__ __forceinline__ float tagf(float v, uint32_t tag) { return __uint_as_float((__float_as_uint(v) & ~1u) | tag); }
__device__ __forceinline__ float untag(float v) { return __uint_as_float(__float_as_uint(v) & ~1u); }
__device__ __forceinline__ void st_x2(float2* p, float a, float b) { asm volatile("st.relaxed.gpu.global.v2.f32 [%0], {%1,%2};" ::"l"(p), "f"(a), "f"(b) : "memory"); }
__device__ __forceinline__ float2 ld_x2(const float2* p) { float2 v; asm volatile("ld.relaxed.gpu.global.v2.f32 {%0,%1}, [%2];" : "=f"(v.x), "=f"(v.y) : "l"(p) : "memory"); return v; }
__device__ __forceinline__ void st_u2(uint2* p, uint32_t a, uint32_t b) { asm volatile("st.relaxed.gpu.global.v2.u32 [%0], {%1,%2};" ::"l"(p), "r"(a), "r"(b) : "memory"); }
__device__ __forceinline__ void prefetch2d(const CUtensorMap* m, int c0, int c1) { asm volatile("cp.async.bulk.prefetch.tensor.2d.L2.global [%0, {%1, %2}];" ::"l"(m), "r"(c0), "r"(c1) : "memory"); }
__device__ __forceinline__ void prefetch1d(const void* p, uint32_t bytes) { asm volatile("cp.async.bulk.prefetch.L2.global [%0], %1;" ::"l"(p), "r"(bytes) : "memory"); }
__device__ __forceinline__ uint32_t ld_x1(const void* p) { uint32_t v; asm volatile("ld.relaxed.gpu.global.u32 %0, [%1];" : "=r"(v) : "l"(p) : "memory"); return v; }
__device__ __forceinline__ uint4 ld_x4(const void* p) { uint4 v; asm volatile("ld.relaxed.gpu.global.v4.u32 {%0,%1,%2,%3}, [%4];" : "=r"(v.x), "=r"(v.y), "=r"(v.z), "=r"(v.w) : "l"(p) : "memory"); return v; }
__device__ __forceinline__ void st_x4(void* p, uint32_t a, uint32_t b, uint32_t c, uint32_t d) { asm volatile("st.relaxed.gpu.global.v4.u32 [%0], {%1,%2,%3,%4};" ::"l"(p), "r"(a), "r"(b), "r"(c), "r"(d) : "memory"); }
__device__ __forceinline__ uint32_t mapa(uint32_t a, uint32_t cta) { uint32_t r; asm volatile("mapa.shared::cluster.u32 %0, %1, %2;" : "=r"(r) : "r"(a), "r"(cta)); return r; }
__device__ __forceinline__ void hint_add(unsigned* p) { asm volatile("red.relaxed.gpu.global.add.u32 [%0], 1;" ::"l"(p) : "memory"); }
__device__ __forceinline__ void hint_wait(const unsigned* p, unsigned target) {
  const uint32_t t0 = (uint32_t)clock();
  while ((int)(ld_x1(p) - target) < 0) spin_guard(t0);
}
__device__ __forceinline__ void tma2d(uint32_t dst, const CUtensorMap* m, uint32_t bar, int c0, int c1) {
  asm volatile("cp.async.bulk.tensor.2d.shared::cluster.global.mbarrier::complete_tx::bytes [%0], [%1, {%3, %4}], [%2];" ::"r"(dst), "l"(m), "r"(bar), "r"(c0), "r"(c1) : "memory");
}
__device__ __forceinline__ void tma3d(uint32_t dst, const CUtensorMap* m, uint32_t bar, int c0, int c1, int c2) {
  asm volatile("cp.async.bulk.tensor.3d.shared::cluster.global.mbarrier::complete_tx::bytes [%0], [%1, {%3, %4, %5}], [%2];" ::"r"(dst), "l"(m), "r"(bar), "r"(c0), "r"(c1), "r"(c2) : "memory");
}
__device__ __forceinline__ void tma4d(uint32_t dst, const CUtensorMap* m, uint32_t bar, int c0, int c1, int c2, int c3) {
  asm volatile("cp.async.bulk.tensor.4d.shared::cluster.global.mbarrier::complete_tx::bytes [%0], [%1, {%3, %4, %5, %6}], [%2];" ::"r"(dst), "l"(m), "r"(bar), "r"(c0), "r"(c1), "r"(c2), "r"(c3) : "memory");
}
__device__ __forceinline__ void wg_fence() { asm volatile("wgmma.fence.sync.aligned;" ::: "memory"); }
__device__ __forceinline__ void wg_commit() { asm volatile("wgmma.commit_group.sync.aligned;" ::: "memory"); }
template <int N> __device__ __forceinline__ void wg_wait() { asm volatile("wgmma.wait_group.sync.aligned %0;" ::"n"(N) : "memory"); }
template <int O, int N, int NN> __device__ __forceinline__ void fence_regs(float (&d)[NN]) {
#pragma unroll
  for (int i = 0; i < N; i++) asm volatile("" : "+f"(d[O + i])::"memory");
}
__device__ __forceinline__ uint32_t pack_bf16(float lo, float hi) {
  uint32_t r; asm("cvt.rn.bf16x2.f32 %0, %1, %2;" : "=r"(r) : "f"(hi), "f"(lo)); return r;
}
__device__ __forceinline__ uint32_t pack_pin(float lo, float hi) {
  uint32_t r; asm volatile("cvt.rn.bf16x2.f32 %0, %1, %2;" : "=r"(r) : "f"(hi), "f"(lo) : "memory"); return r;
}
__device__ __forceinline__ float bf_lo(uint32_t u) { return __uint_as_float(u << 16); }
__device__ __forceinline__ float bf_hi(uint32_t u) { return __uint_as_float(u & 0xffff0000u); }

__device__ __forceinline__ uint64_t d128(uint32_t lo) { uint64_t d; asm("mov.b64 %0, {%1, 0x40000040};" : "=l"(d) : "r"(lo)); return d; }
__device__ __forceinline__ uint64_t d64(uint32_t lo) { uint64_t d; asm("mov.b64 %0, {%1, 0x80000020};" : "=l"(d) : "r"(lo)); return d; }
template<int O,int TB,int ACC,int NN> __device__ __forceinline__ void mma_ss64(float (&d)[NN], uint64_t da, uint64_t db, int sd = 0){
  if constexpr (ACC == 1) asm volatile("wgmma.mma_async.sync.aligned.m64n64k16.f32.bf16.bf16 {%0,%1,%2,%3,%4,%5,%6,%7,%8,%9,%10,%11,%12,%13,%14,%15,%16,%17,%18,%19,%20,%21,%22,%23,%24,%25,%26,%27,%28,%29,%30,%31}, %32, %33, 1, 1, 1, 0, %34;"
   : "+f"(d[O+0]), "+f"(d[O+1]), "+f"(d[O+2]), "+f"(d[O+3]), "+f"(d[O+4]), "+f"(d[O+5]), "+f"(d[O+6]), "+f"(d[O+7]), "+f"(d[O+8]), "+f"(d[O+9]), "+f"(d[O+10]), "+f"(d[O+11]), "+f"(d[O+12]), "+f"(d[O+13]), "+f"(d[O+14]), "+f"(d[O+15]), "+f"(d[O+16]), "+f"(d[O+17]), "+f"(d[O+18]), "+f"(d[O+19]), "+f"(d[O+20]), "+f"(d[O+21]), "+f"(d[O+22]), "+f"(d[O+23]), "+f"(d[O+24]), "+f"(d[O+25]), "+f"(d[O+26]), "+f"(d[O+27]), "+f"(d[O+28]), "+f"(d[O+29]), "+f"(d[O+30]), "+f"(d[O+31])
   : "l"(da), "l"(db), "n"(TB));
  else if constexpr (ACC == 0) asm volatile("wgmma.mma_async.sync.aligned.m64n64k16.f32.bf16.bf16 {%0,%1,%2,%3,%4,%5,%6,%7,%8,%9,%10,%11,%12,%13,%14,%15,%16,%17,%18,%19,%20,%21,%22,%23,%24,%25,%26,%27,%28,%29,%30,%31}, %32, %33, 0, 1, 1, 0, %34;"
   : "=f"(d[O+0]), "=f"(d[O+1]), "=f"(d[O+2]), "=f"(d[O+3]), "=f"(d[O+4]), "=f"(d[O+5]), "=f"(d[O+6]), "=f"(d[O+7]), "=f"(d[O+8]), "=f"(d[O+9]), "=f"(d[O+10]), "=f"(d[O+11]), "=f"(d[O+12]), "=f"(d[O+13]), "=f"(d[O+14]), "=f"(d[O+15]), "=f"(d[O+16]), "=f"(d[O+17]), "=f"(d[O+18]), "=f"(d[O+19]), "=f"(d[O+20]), "=f"(d[O+21]), "=f"(d[O+22]), "=f"(d[O+23]), "=f"(d[O+24]), "=f"(d[O+25]), "=f"(d[O+26]), "=f"(d[O+27]), "=f"(d[O+28]), "=f"(d[O+29]), "=f"(d[O+30]), "=f"(d[O+31])
   : "l"(da), "l"(db), "n"(TB));
  else asm volatile("{\n.reg .pred p;\nsetp.ne.b32 p, %35, 0;\nwgmma.mma_async.sync.aligned.m64n64k16.f32.bf16.bf16 {%0,%1,%2,%3,%4,%5,%6,%7,%8,%9,%10,%11,%12,%13,%14,%15,%16,%17,%18,%19,%20,%21,%22,%23,%24,%25,%26,%27,%28,%29,%30,%31}, %32, %33, p, 1, 1, 0, %34;\n}"
   : "+f"(d[O+0]), "+f"(d[O+1]), "+f"(d[O+2]), "+f"(d[O+3]), "+f"(d[O+4]), "+f"(d[O+5]), "+f"(d[O+6]), "+f"(d[O+7]), "+f"(d[O+8]), "+f"(d[O+9]), "+f"(d[O+10]), "+f"(d[O+11]), "+f"(d[O+12]), "+f"(d[O+13]), "+f"(d[O+14]), "+f"(d[O+15]), "+f"(d[O+16]), "+f"(d[O+17]), "+f"(d[O+18]), "+f"(d[O+19]), "+f"(d[O+20]), "+f"(d[O+21]), "+f"(d[O+22]), "+f"(d[O+23]), "+f"(d[O+24]), "+f"(d[O+25]), "+f"(d[O+26]), "+f"(d[O+27]), "+f"(d[O+28]), "+f"(d[O+29]), "+f"(d[O+30]), "+f"(d[O+31])
   : "l"(da), "l"(db), "n"(TB), "r"(sd));
}
template<int O,int TB,int ACC,int NN> __device__ __forceinline__ void mma_rs64(float (&d)[NN], uint32_t a0, uint32_t a1, uint32_t a2, uint32_t a3, uint64_t db, int sd = 0){
  if constexpr (ACC == 1) asm volatile("wgmma.mma_async.sync.aligned.m64n64k16.f32.bf16.bf16 {%0,%1,%2,%3,%4,%5,%6,%7,%8,%9,%10,%11,%12,%13,%14,%15,%16,%17,%18,%19,%20,%21,%22,%23,%24,%25,%26,%27,%28,%29,%30,%31}, {%32,%33,%34,%35}, %36, 1, 1, 1, %37;"
   : "+f"(d[O+0]), "+f"(d[O+1]), "+f"(d[O+2]), "+f"(d[O+3]), "+f"(d[O+4]), "+f"(d[O+5]), "+f"(d[O+6]), "+f"(d[O+7]), "+f"(d[O+8]), "+f"(d[O+9]), "+f"(d[O+10]), "+f"(d[O+11]), "+f"(d[O+12]), "+f"(d[O+13]), "+f"(d[O+14]), "+f"(d[O+15]), "+f"(d[O+16]), "+f"(d[O+17]), "+f"(d[O+18]), "+f"(d[O+19]), "+f"(d[O+20]), "+f"(d[O+21]), "+f"(d[O+22]), "+f"(d[O+23]), "+f"(d[O+24]), "+f"(d[O+25]), "+f"(d[O+26]), "+f"(d[O+27]), "+f"(d[O+28]), "+f"(d[O+29]), "+f"(d[O+30]), "+f"(d[O+31])
   : "r"(a0), "r"(a1), "r"(a2), "r"(a3), "l"(db), "n"(TB));
  else if constexpr (ACC == 0) asm volatile("wgmma.mma_async.sync.aligned.m64n64k16.f32.bf16.bf16 {%0,%1,%2,%3,%4,%5,%6,%7,%8,%9,%10,%11,%12,%13,%14,%15,%16,%17,%18,%19,%20,%21,%22,%23,%24,%25,%26,%27,%28,%29,%30,%31}, {%32,%33,%34,%35}, %36, 0, 1, 1, %37;"
   : "=f"(d[O+0]), "=f"(d[O+1]), "=f"(d[O+2]), "=f"(d[O+3]), "=f"(d[O+4]), "=f"(d[O+5]), "=f"(d[O+6]), "=f"(d[O+7]), "=f"(d[O+8]), "=f"(d[O+9]), "=f"(d[O+10]), "=f"(d[O+11]), "=f"(d[O+12]), "=f"(d[O+13]), "=f"(d[O+14]), "=f"(d[O+15]), "=f"(d[O+16]), "=f"(d[O+17]), "=f"(d[O+18]), "=f"(d[O+19]), "=f"(d[O+20]), "=f"(d[O+21]), "=f"(d[O+22]), "=f"(d[O+23]), "=f"(d[O+24]), "=f"(d[O+25]), "=f"(d[O+26]), "=f"(d[O+27]), "=f"(d[O+28]), "=f"(d[O+29]), "=f"(d[O+30]), "=f"(d[O+31])
   : "r"(a0), "r"(a1), "r"(a2), "r"(a3), "l"(db), "n"(TB));
  else asm volatile("{\n.reg .pred p;\nsetp.ne.b32 p, %38, 0;\nwgmma.mma_async.sync.aligned.m64n64k16.f32.bf16.bf16 {%0,%1,%2,%3,%4,%5,%6,%7,%8,%9,%10,%11,%12,%13,%14,%15,%16,%17,%18,%19,%20,%21,%22,%23,%24,%25,%26,%27,%28,%29,%30,%31}, {%32,%33,%34,%35}, %36, p, 1, 1, %37;\n}"
   : "+f"(d[O+0]), "+f"(d[O+1]), "+f"(d[O+2]), "+f"(d[O+3]), "+f"(d[O+4]), "+f"(d[O+5]), "+f"(d[O+6]), "+f"(d[O+7]), "+f"(d[O+8]), "+f"(d[O+9]), "+f"(d[O+10]), "+f"(d[O+11]), "+f"(d[O+12]), "+f"(d[O+13]), "+f"(d[O+14]), "+f"(d[O+15]), "+f"(d[O+16]), "+f"(d[O+17]), "+f"(d[O+18]), "+f"(d[O+19]), "+f"(d[O+20]), "+f"(d[O+21]), "+f"(d[O+22]), "+f"(d[O+23]), "+f"(d[O+24]), "+f"(d[O+25]), "+f"(d[O+26]), "+f"(d[O+27]), "+f"(d[O+28]), "+f"(d[O+29]), "+f"(d[O+30]), "+f"(d[O+31])
   : "r"(a0), "r"(a1), "r"(a2), "r"(a3), "l"(db), "n"(TB), "r"(sd));
}
template<int O,int TB,int ACC,int NN> __device__ __forceinline__ void mma_ss128(float (&d)[NN], uint64_t da, uint64_t db, int sd = 0){
  if constexpr (ACC == 1) asm volatile("wgmma.mma_async.sync.aligned.m64n128k16.f32.bf16.bf16 {%0,%1,%2,%3,%4,%5,%6,%7,%8,%9,%10,%11,%12,%13,%14,%15,%16,%17,%18,%19,%20,%21,%22,%23,%24,%25,%26,%27,%28,%29,%30,%31,%32,%33,%34,%35,%36,%37,%38,%39,%40,%41,%42,%43,%44,%45,%46,%47,%48,%49,%50,%51,%52,%53,%54,%55,%56,%57,%58,%59,%60,%61,%62,%63}, %64, %65, 1, 1, 1, 0, %66;"
   : "+f"(d[O+0]), "+f"(d[O+1]), "+f"(d[O+2]), "+f"(d[O+3]), "+f"(d[O+4]), "+f"(d[O+5]), "+f"(d[O+6]), "+f"(d[O+7]), "+f"(d[O+8]), "+f"(d[O+9]), "+f"(d[O+10]), "+f"(d[O+11]), "+f"(d[O+12]), "+f"(d[O+13]), "+f"(d[O+14]), "+f"(d[O+15]), "+f"(d[O+16]), "+f"(d[O+17]), "+f"(d[O+18]), "+f"(d[O+19]), "+f"(d[O+20]), "+f"(d[O+21]), "+f"(d[O+22]), "+f"(d[O+23]), "+f"(d[O+24]), "+f"(d[O+25]), "+f"(d[O+26]), "+f"(d[O+27]), "+f"(d[O+28]), "+f"(d[O+29]), "+f"(d[O+30]), "+f"(d[O+31]), "+f"(d[O+32]), "+f"(d[O+33]), "+f"(d[O+34]), "+f"(d[O+35]), "+f"(d[O+36]), "+f"(d[O+37]), "+f"(d[O+38]), "+f"(d[O+39]), "+f"(d[O+40]), "+f"(d[O+41]), "+f"(d[O+42]), "+f"(d[O+43]), "+f"(d[O+44]), "+f"(d[O+45]), "+f"(d[O+46]), "+f"(d[O+47]), "+f"(d[O+48]), "+f"(d[O+49]), "+f"(d[O+50]), "+f"(d[O+51]), "+f"(d[O+52]), "+f"(d[O+53]), "+f"(d[O+54]), "+f"(d[O+55]), "+f"(d[O+56]), "+f"(d[O+57]), "+f"(d[O+58]), "+f"(d[O+59]), "+f"(d[O+60]), "+f"(d[O+61]), "+f"(d[O+62]), "+f"(d[O+63])
   : "l"(da), "l"(db), "n"(TB));
  else if constexpr (ACC == 0) asm volatile("wgmma.mma_async.sync.aligned.m64n128k16.f32.bf16.bf16 {%0,%1,%2,%3,%4,%5,%6,%7,%8,%9,%10,%11,%12,%13,%14,%15,%16,%17,%18,%19,%20,%21,%22,%23,%24,%25,%26,%27,%28,%29,%30,%31,%32,%33,%34,%35,%36,%37,%38,%39,%40,%41,%42,%43,%44,%45,%46,%47,%48,%49,%50,%51,%52,%53,%54,%55,%56,%57,%58,%59,%60,%61,%62,%63}, %64, %65, 0, 1, 1, 0, %66;"
   : "=f"(d[O+0]), "=f"(d[O+1]), "=f"(d[O+2]), "=f"(d[O+3]), "=f"(d[O+4]), "=f"(d[O+5]), "=f"(d[O+6]), "=f"(d[O+7]), "=f"(d[O+8]), "=f"(d[O+9]), "=f"(d[O+10]), "=f"(d[O+11]), "=f"(d[O+12]), "=f"(d[O+13]), "=f"(d[O+14]), "=f"(d[O+15]), "=f"(d[O+16]), "=f"(d[O+17]), "=f"(d[O+18]), "=f"(d[O+19]), "=f"(d[O+20]), "=f"(d[O+21]), "=f"(d[O+22]), "=f"(d[O+23]), "=f"(d[O+24]), "=f"(d[O+25]), "=f"(d[O+26]), "=f"(d[O+27]), "=f"(d[O+28]), "=f"(d[O+29]), "=f"(d[O+30]), "=f"(d[O+31]), "=f"(d[O+32]), "=f"(d[O+33]), "=f"(d[O+34]), "=f"(d[O+35]), "=f"(d[O+36]), "=f"(d[O+37]), "=f"(d[O+38]), "=f"(d[O+39]), "=f"(d[O+40]), "=f"(d[O+41]), "=f"(d[O+42]), "=f"(d[O+43]), "=f"(d[O+44]), "=f"(d[O+45]), "=f"(d[O+46]), "=f"(d[O+47]), "=f"(d[O+48]), "=f"(d[O+49]), "=f"(d[O+50]), "=f"(d[O+51]), "=f"(d[O+52]), "=f"(d[O+53]), "=f"(d[O+54]), "=f"(d[O+55]), "=f"(d[O+56]), "=f"(d[O+57]), "=f"(d[O+58]), "=f"(d[O+59]), "=f"(d[O+60]), "=f"(d[O+61]), "=f"(d[O+62]), "=f"(d[O+63])
   : "l"(da), "l"(db), "n"(TB));
  else asm volatile("{\n.reg .pred p;\nsetp.ne.b32 p, %67, 0;\nwgmma.mma_async.sync.aligned.m64n128k16.f32.bf16.bf16 {%0,%1,%2,%3,%4,%5,%6,%7,%8,%9,%10,%11,%12,%13,%14,%15,%16,%17,%18,%19,%20,%21,%22,%23,%24,%25,%26,%27,%28,%29,%30,%31,%32,%33,%34,%35,%36,%37,%38,%39,%40,%41,%42,%43,%44,%45,%46,%47,%48,%49,%50,%51,%52,%53,%54,%55,%56,%57,%58,%59,%60,%61,%62,%63}, %64, %65, p, 1, 1, 0, %66;\n}"
   : "+f"(d[O+0]), "+f"(d[O+1]), "+f"(d[O+2]), "+f"(d[O+3]), "+f"(d[O+4]), "+f"(d[O+5]), "+f"(d[O+6]), "+f"(d[O+7]), "+f"(d[O+8]), "+f"(d[O+9]), "+f"(d[O+10]), "+f"(d[O+11]), "+f"(d[O+12]), "+f"(d[O+13]), "+f"(d[O+14]), "+f"(d[O+15]), "+f"(d[O+16]), "+f"(d[O+17]), "+f"(d[O+18]), "+f"(d[O+19]), "+f"(d[O+20]), "+f"(d[O+21]), "+f"(d[O+22]), "+f"(d[O+23]), "+f"(d[O+24]), "+f"(d[O+25]), "+f"(d[O+26]), "+f"(d[O+27]), "+f"(d[O+28]), "+f"(d[O+29]), "+f"(d[O+30]), "+f"(d[O+31]), "+f"(d[O+32]), "+f"(d[O+33]), "+f"(d[O+34]), "+f"(d[O+35]), "+f"(d[O+36]), "+f"(d[O+37]), "+f"(d[O+38]), "+f"(d[O+39]), "+f"(d[O+40]), "+f"(d[O+41]), "+f"(d[O+42]), "+f"(d[O+43]), "+f"(d[O+44]), "+f"(d[O+45]), "+f"(d[O+46]), "+f"(d[O+47]), "+f"(d[O+48]), "+f"(d[O+49]), "+f"(d[O+50]), "+f"(d[O+51]), "+f"(d[O+52]), "+f"(d[O+53]), "+f"(d[O+54]), "+f"(d[O+55]), "+f"(d[O+56]), "+f"(d[O+57]), "+f"(d[O+58]), "+f"(d[O+59]), "+f"(d[O+60]), "+f"(d[O+61]), "+f"(d[O+62]), "+f"(d[O+63])
   : "l"(da), "l"(db), "n"(TB), "r"(sd));
}
template<int O,int TB,int ACC,int NN> __device__ __forceinline__ void mma_rs128(float (&d)[NN], uint32_t a0, uint32_t a1, uint32_t a2, uint32_t a3, uint64_t db, int sd = 0){
  if constexpr (ACC == 1) asm volatile("wgmma.mma_async.sync.aligned.m64n128k16.f32.bf16.bf16 {%0,%1,%2,%3,%4,%5,%6,%7,%8,%9,%10,%11,%12,%13,%14,%15,%16,%17,%18,%19,%20,%21,%22,%23,%24,%25,%26,%27,%28,%29,%30,%31,%32,%33,%34,%35,%36,%37,%38,%39,%40,%41,%42,%43,%44,%45,%46,%47,%48,%49,%50,%51,%52,%53,%54,%55,%56,%57,%58,%59,%60,%61,%62,%63}, {%64,%65,%66,%67}, %68, 1, 1, 1, %69;"
   : "+f"(d[O+0]), "+f"(d[O+1]), "+f"(d[O+2]), "+f"(d[O+3]), "+f"(d[O+4]), "+f"(d[O+5]), "+f"(d[O+6]), "+f"(d[O+7]), "+f"(d[O+8]), "+f"(d[O+9]), "+f"(d[O+10]), "+f"(d[O+11]), "+f"(d[O+12]), "+f"(d[O+13]), "+f"(d[O+14]), "+f"(d[O+15]), "+f"(d[O+16]), "+f"(d[O+17]), "+f"(d[O+18]), "+f"(d[O+19]), "+f"(d[O+20]), "+f"(d[O+21]), "+f"(d[O+22]), "+f"(d[O+23]), "+f"(d[O+24]), "+f"(d[O+25]), "+f"(d[O+26]), "+f"(d[O+27]), "+f"(d[O+28]), "+f"(d[O+29]), "+f"(d[O+30]), "+f"(d[O+31]), "+f"(d[O+32]), "+f"(d[O+33]), "+f"(d[O+34]), "+f"(d[O+35]), "+f"(d[O+36]), "+f"(d[O+37]), "+f"(d[O+38]), "+f"(d[O+39]), "+f"(d[O+40]), "+f"(d[O+41]), "+f"(d[O+42]), "+f"(d[O+43]), "+f"(d[O+44]), "+f"(d[O+45]), "+f"(d[O+46]), "+f"(d[O+47]), "+f"(d[O+48]), "+f"(d[O+49]), "+f"(d[O+50]), "+f"(d[O+51]), "+f"(d[O+52]), "+f"(d[O+53]), "+f"(d[O+54]), "+f"(d[O+55]), "+f"(d[O+56]), "+f"(d[O+57]), "+f"(d[O+58]), "+f"(d[O+59]), "+f"(d[O+60]), "+f"(d[O+61]), "+f"(d[O+62]), "+f"(d[O+63])
   : "r"(a0), "r"(a1), "r"(a2), "r"(a3), "l"(db), "n"(TB));
  else if constexpr (ACC == 0) asm volatile("wgmma.mma_async.sync.aligned.m64n128k16.f32.bf16.bf16 {%0,%1,%2,%3,%4,%5,%6,%7,%8,%9,%10,%11,%12,%13,%14,%15,%16,%17,%18,%19,%20,%21,%22,%23,%24,%25,%26,%27,%28,%29,%30,%31,%32,%33,%34,%35,%36,%37,%38,%39,%40,%41,%42,%43,%44,%45,%46,%47,%48,%49,%50,%51,%52,%53,%54,%55,%56,%57,%58,%59,%60,%61,%62,%63}, {%64,%65,%66,%67}, %68, 0, 1, 1, %69;"
   : "=f"(d[O+0]), "=f"(d[O+1]), "=f"(d[O+2]), "=f"(d[O+3]), "=f"(d[O+4]), "=f"(d[O+5]), "=f"(d[O+6]), "=f"(d[O+7]), "=f"(d[O+8]), "=f"(d[O+9]), "=f"(d[O+10]), "=f"(d[O+11]), "=f"(d[O+12]), "=f"(d[O+13]), "=f"(d[O+14]), "=f"(d[O+15]), "=f"(d[O+16]), "=f"(d[O+17]), "=f"(d[O+18]), "=f"(d[O+19]), "=f"(d[O+20]), "=f"(d[O+21]), "=f"(d[O+22]), "=f"(d[O+23]), "=f"(d[O+24]), "=f"(d[O+25]), "=f"(d[O+26]), "=f"(d[O+27]), "=f"(d[O+28]), "=f"(d[O+29]), "=f"(d[O+30]), "=f"(d[O+31]), "=f"(d[O+32]), "=f"(d[O+33]), "=f"(d[O+34]), "=f"(d[O+35]), "=f"(d[O+36]), "=f"(d[O+37]), "=f"(d[O+38]), "=f"(d[O+39]), "=f"(d[O+40]), "=f"(d[O+41]), "=f"(d[O+42]), "=f"(d[O+43]), "=f"(d[O+44]), "=f"(d[O+45]), "=f"(d[O+46]), "=f"(d[O+47]), "=f"(d[O+48]), "=f"(d[O+49]), "=f"(d[O+50]), "=f"(d[O+51]), "=f"(d[O+52]), "=f"(d[O+53]), "=f"(d[O+54]), "=f"(d[O+55]), "=f"(d[O+56]), "=f"(d[O+57]), "=f"(d[O+58]), "=f"(d[O+59]), "=f"(d[O+60]), "=f"(d[O+61]), "=f"(d[O+62]), "=f"(d[O+63])
   : "r"(a0), "r"(a1), "r"(a2), "r"(a3), "l"(db), "n"(TB));
  else asm volatile("{\n.reg .pred p;\nsetp.ne.b32 p, %70, 0;\nwgmma.mma_async.sync.aligned.m64n128k16.f32.bf16.bf16 {%0,%1,%2,%3,%4,%5,%6,%7,%8,%9,%10,%11,%12,%13,%14,%15,%16,%17,%18,%19,%20,%21,%22,%23,%24,%25,%26,%27,%28,%29,%30,%31,%32,%33,%34,%35,%36,%37,%38,%39,%40,%41,%42,%43,%44,%45,%46,%47,%48,%49,%50,%51,%52,%53,%54,%55,%56,%57,%58,%59,%60,%61,%62,%63}, {%64,%65,%66,%67}, %68, p, 1, 1, %69;\n}"
   : "+f"(d[O+0]), "+f"(d[O+1]), "+f"(d[O+2]), "+f"(d[O+3]), "+f"(d[O+4]), "+f"(d[O+5]), "+f"(d[O+6]), "+f"(d[O+7]), "+f"(d[O+8]), "+f"(d[O+9]), "+f"(d[O+10]), "+f"(d[O+11]), "+f"(d[O+12]), "+f"(d[O+13]), "+f"(d[O+14]), "+f"(d[O+15]), "+f"(d[O+16]), "+f"(d[O+17]), "+f"(d[O+18]), "+f"(d[O+19]), "+f"(d[O+20]), "+f"(d[O+21]), "+f"(d[O+22]), "+f"(d[O+23]), "+f"(d[O+24]), "+f"(d[O+25]), "+f"(d[O+26]), "+f"(d[O+27]), "+f"(d[O+28]), "+f"(d[O+29]), "+f"(d[O+30]), "+f"(d[O+31]), "+f"(d[O+32]), "+f"(d[O+33]), "+f"(d[O+34]), "+f"(d[O+35]), "+f"(d[O+36]), "+f"(d[O+37]), "+f"(d[O+38]), "+f"(d[O+39]), "+f"(d[O+40]), "+f"(d[O+41]), "+f"(d[O+42]), "+f"(d[O+43]), "+f"(d[O+44]), "+f"(d[O+45]), "+f"(d[O+46]), "+f"(d[O+47]), "+f"(d[O+48]), "+f"(d[O+49]), "+f"(d[O+50]), "+f"(d[O+51]), "+f"(d[O+52]), "+f"(d[O+53]), "+f"(d[O+54]), "+f"(d[O+55]), "+f"(d[O+56]), "+f"(d[O+57]), "+f"(d[O+58]), "+f"(d[O+59]), "+f"(d[O+60]), "+f"(d[O+61]), "+f"(d[O+62]), "+f"(d[O+63])
   : "r"(a0), "r"(a1), "r"(a2), "r"(a3), "l"(db), "n"(TB), "r"(sd));
}

__host__ __device__ constexpr int brev(int a, int bits) { int r = 0; for (int i = 0; i < bits; i++) r |= ((a >> i) & 1) << (bits - 1 - i); return r; }
__host__ __device__ constexpr int ilog2(int n) { return n <= 1 ? 0 : 1 + ilog2(n / 2); }
template <int SG, int A> __device__ __forceinline__ void bfly(float2& a, float2& b) {
  if constexpr (A == 0) {
    float tr = a.x - b.x, ti = a.y - b.y; a.x += b.x; a.y += b.y; b.x = tr; b.y = ti;
  } else if constexpr (A == 8) {
    float pr = SG > 0 ? -b.y : b.y, pi = SG > 0 ? b.x : -b.x;
    b.x = a.x - pr; b.y = a.y - pi; a.x += pr; a.y += pi;
  } else {
    constexpr float wr = tbl::W32<A>::c, wi = SG * tbl::W32<A>::s;
    float tr = fmaf(wr, b.x, a.x), ti = fmaf(wr, b.y, a.y);
    tr = fmaf(-wi, b.y, tr); ti = fmaf(wi, b.x, ti);
    b.x = fmaf(2.f, a.x, -tr); b.y = fmaf(2.f, a.y, -ti); a.x = tr; a.y = ti;
  }
}
template <int SG, int N, int O, int ST, int A> __device__ __forceinline__ void dft_comb(float2 (&x)[32]) {
  if constexpr (A < N / 2) {
    constexpr int p = O + 2 * ST * brev(A, ilog2(N / 2));
    bfly<SG, A * (32 / N)>(x[p], x[p + ST]);
    dft_comb<SG, N, O, ST, A + 1>(x);
  }
}
template <int SG, int N, int O, int ST> __device__ __forceinline__ void dft(float2 (&x)[32]) {
  if constexpr (N > 1) {
    dft<SG, N / 2, O, 2 * ST>(x);
    dft<SG, N / 2, O + ST, 2 * ST>(x);
    dft_comb<SG, N, O, ST, 0>(x);
  }
}

#define NEARLY 2
#define XAHEAD 3
#define WAFTER 3
#define WPACE 50
#define GATE_AT 0
#define TPACE 40
#define PFMODE 0
#define MAPMODE 0
template <int V> struct IC { static constexpr int value = V; };
struct Maps { CUtensorMap ft, g32, x, u32, g64, u64, e, wr, wi, d192, d32, fg; };

constexpr int NCTA = 132;
constexpr int U = 16384;
constexpr int TB = 36864;
constexpr int NR = 5;
constexpr int OFF_RING = 8 * U, OFF_Z = 9 * U, OFF_T = 13 * U;
constexpr int OFF_BAR = 14 * U;
constexpr int SMEM_BYTES = OFF_BAR + 512;
constexpr int B_FX = 0, B_FA = 8, B_FT = 13, B_Z = 17, B_W = 21, B_HX = 22, B_HT = 23, B_HP = 24;
constexpr int B_EA = 27, B_ET = 32, B_RDY = 36;
constexpr int B_T = 37, NBAR = 38;
__host__ __device__ constexpr int rslot(int n) { return (n + 2) % NR; }
__host__ __device__ constexpr int rpar(int n) { return (n / NR) & 1; }

__global__ void __cluster_dims__(2, 1, 1) __launch_bounds__(512, 1)
fused_kernel(const __grid_constant__ Maps maps, const __nv_bfloat16* __restrict__ x, const __nv_bfloat16* __restrict__ w_r,
             const __nv_bfloat16* __restrict__ w_i, const __nv_bfloat16* __restrict__ gate_w, const __nv_bfloat16* __restrict__ Wg,
             const __nv_bfloat16* __restrict__ Wu, __nv_bfloat16* __restrict__ out) {
  extern __shared__ __align__(1024) uint8_t smem[];
  const uint32_t sb = smem_u32(smem);
  const uint32_t bars = sb + OFF_BAR;
  const int tid = threadIdx.x, lane = tid & 31;
  const int warp = __shfl_sync(0xffffffffu, tid >> 5, 0);
  const bool helper = blockIdx.x >= 128;
  const int cl = (blockIdx.x >> 1) & 63, rank = blockIdx.x & 1;
  const int q4 = cl & 3, rb = cl >> 2;
  const int j = 2 * q4 + rank;
  const int f_full = 448 * q4 + (rank ? 256 : 0);
  const int f_half = 448 * q4 + (rank ? 224 : 192);
  const int kg = 2 * j + (rb >> 3), tn = rb & 7;

  if (tid == 64) { PROF_EV(0); PROF_CK(40); }
  auto ring_part = [&](int p, int n, int slot) {
    const uint32_t fb = bars + 8 * (B_FA + slot), dst = sb + OFF_RING + slot * U;
    const bool table = n == 9 || n == 10 || n >= 34;
    const int q = n == 8 ? 0 : n - 10;
    if (p == 0) {
      mbar_expect_tx(fb, U);
      if (n < 8) tma2d(dst, &maps.ft, fb, 64 * n, 64 * j);
      else if (table) tma4d(dst, &maps.e, fb, 0, 0, 0, 2 * rb + (n >= 34 ? n - 34 : n - 9));
      else tma2d(dst, &maps.g64, fb, f_full + 64 * (q >> 3), 64 * (q & 7));
    } else if (p == 1) {
      if (n < 8) { tma2d(dst + 8192, &maps.g32, fb, f_half, 64 * n); tma2d(dst + 12288, &maps.u32, fb, f_half, 64 * n); }
      else if (!table) tma2d(dst + 8192, &maps.u64, fb, f_full + 64 * (q >> 3), 64 * (q & 7));
    }
  };
  auto x_load = [&](int q) {
    mbar_expect_tx(bars + 8 * (B_FX + q), U);
    tma3d(sb + q * U, &maps.x, bars + 8 * (B_FX + q), 64 * q, 0, 2 * rb);
  };
  if (warp < 8) {
    if (!helper) {
      const int r8 = tid >> 3, c8 = tid & 7, r4 = tid >> 2, c4 = tid & 3;
      const uint32_t sw8 = r8 * 128 + ((c8 ^ (r8 & 7)) << 4), sw4 = r4 * 64 + ((c4 ^ ((r4 >> 1) & 3)) << 4);
      const __nv_bfloat16* px = x + (size_t)(2 * rb + 32 * r8) * 512 + 8 * c8;
      const uint16_t* pf = g_FT.v + (64 * j + r8) * 512 + 8 * c8;
      const size_t om = (size_t)r4 * 1792 + f_half + 8 * c4;
#pragma unroll
      for (int kb = 0; kb < NEARLY; kb++) {
        const uint32_t dst = sb + OFF_RING + rslot(kb) * U;
#pragma unroll
        for (int i = 0; i < 4; i++) cp16(sb + kb * U + i * 4096 + sw8, px + (i & 1) * 32 * 32 * 512 + (i >> 1) * 512 + 64 * kb);
        cp16(dst + sw8, pf + 64 * kb); cp16(dst + 4096 + sw8, pf + 32 * 512 + 64 * kb);
        cp16(dst + 8192 + sw4, Wg + om + kb * 64 * 1792); cp16(dst + 12288 + sw4, Wu + om + kb * 64 * 1792);
        asm volatile("cp.async.commit_group;" ::: "memory");
      }
    }
  } else if (warp >= 12 && lane == 0) {
    asm volatile("prefetch.tensormap [%0];" ::"l"((const char*)&maps + (warp - 12) * 128) : "memory");
    if (warp == 15) {
#pragma unroll
      for (int i = B_FT; i < NBAR; i++) mbar_init(bars + 8 * i, i < B_EA ? 1 : i < B_T ? 2 : 4);
#pragma unroll
      for (int i = 0; i < 4; i++) mbar_expect_tx(bars + 8 * (B_Z + i), U);
      asm volatile("fence.mbarrier_init.release.cluster;" ::: "memory");
    } else if (warp == 14) {
#pragma unroll
      for (int i = 0; i < B_FT; i++) mbar_init(bars + 8 * i, 1);
#pragma unroll
      for (int i = 0; i < NEARLY; i++) mbar_arrive(bars + 8 * (B_FA + rslot(i)));
    } else if (warp == 13) {
#pragma unroll
      for (int i = 4; i < 12; i++) asm volatile("prefetch.tensormap [%0];" ::"l"((const char*)&maps + i * 128) : "memory");
    }
    asm volatile("fence.proxy.async.shared::cta;" ::: "memory");
  }
  if (warp >= 8) {
    __syncwarp();
    asm volatile("bar.arrive 0, 512;" ::: "memory");
    asm volatile("bar.sync 3, 256;" ::: "memory");
  }
  asm volatile("barrier.cluster.arrive.relaxed.aligned;" ::: "memory");
  if (tid == 64) PROF_EV(38);

  if (warp >= 12) {
    asm volatile("setmaxnreg.dec.sync.aligned.u32 24;");
    if (lane == 0 && !helper) {
      if (warp < 14) {
        int slot = rslot(NEARLY), par = 1;
#pragma unroll 1
        for (int n = NEARLY; n < 36; n++) {
          mbar_wait(bars + 8 * (B_EA + slot), par);
          ring_part(warp - 12, n, slot);
          if (++slot == NR) slot = 0;
          if (slot == rslot(0)) par ^= 1;
        }
      } else if (warp == 15) {
        const unsigned ep1 = ld_x1(&g_epoch[blockIdx.x * 8]) + 1;
        hint_wait(&g_cntX[32 * j], ep1 * 128u); mbar_arrive(bars + 8 * B_HX);
        hint_wait(&g_cntT[32 * j], ep1 * (j == 0 ? 68u : 64u)); mbar_arrive(bars + 8 * B_HT);
#pragma unroll 1
        for (int i = 0; i < 3; i++) { hint_wait(&g_cntP[32 * (rb * 8 + j) + i], ep1 * 8u); mbar_arrive(bars + 8 * (B_HP + i)); }
      } else {
#pragma unroll 1
        for (int q = NEARLY; q < 8; q++) { if (q >= NEARLY + XAHEAD) mbar_wait(bars + 8 * (B_FX + q - XAHEAD), 0); x_load(q); }
        PROF_EV(31);
#pragma unroll 1
        for (int t = 0; t < 8; t++) {
          const int i = t < 3 ? t + 1 : t < 6 ? t - 2 : 0;
          const int col = 64 * (2 * ((q4 + i) & 3) + ((t < 3 || t == 6) ? 1 - rank : rank));
          const uint32_t fb = bars + 8 * (B_FT + (t & 3)), dst = sb + (t & 3) * TB;
          mbar_wait(bars + 8 * (B_ET + (t & 3)), t >> 2);
          mbar_expect_tx(fb, TB);
          tma2d(dst, &maps.d192, fb, col, f_full);
          tma2d(dst + 24576, &maps.d32, fb, col, f_half);
          tma4d(dst + 28672, &maps.fg, fb, col, 0, 0, 4 * j);
        }
      }
    }
  } else if (warp >= 8) {
    asm volatile("setmaxnreg.dec.sync.aligned.u32 88;");
    const int t = tid - 256, w = warp - 8;
    const float scale = 2.0f / (2048.0f * 512.0f);
    const uint32_t ep = ld_x1(&g_epoch[blockIdx.x * 8]);
    const uint32_t tag = (ep + 1) & 1;
    auto gate_rows = [&] {
      uint4 xv[8], gv[2];
#pragma unroll
      for (int i = 0; i < 4; i++) {
        const int r = 16 * j + 4 * w + i;
        const uint4* p = (const uint4*)(x + (size_t)(2 * rb + (r >> 6) + 32 * (r & 63)) * 512) + lane;
        xv[2 * i] = __ldg(p); xv[2 * i + 1] = __ldg(p + 32);
      }
      gv[0] = __ldg((const uint4*)gate_w + lane); gv[1] = __ldg((const uint4*)gate_w + lane + 32);
      {
        float z[4];
#pragma unroll
        for (int i = 0; i < 4; i++) {
          float a = 0.f;
#pragma unroll
          for (int hh = 0; hh < 2; hh++) {
            const uint4 u = xv[2 * i + hh], v = gv[hh];
            a = fmaf(bf_lo(u.x), bf_lo(v.x), a); a = fmaf(bf_hi(u.x), bf_hi(v.x), a);
            a = fmaf(bf_lo(u.y), bf_lo(v.y), a); a = fmaf(bf_hi(u.y), bf_hi(v.y), a);
            a = fmaf(bf_lo(u.z), bf_lo(v.z), a); a = fmaf(bf_hi(u.z), bf_hi(v.z), a);
            a = fmaf(bf_lo(u.w), bf_lo(v.w), a); a = fmaf(bf_hi(u.w), bf_hi(v.w), a);
          }
#pragma unroll
          for (int o = 16; o; o >>= 1) a += __shfl_xor_sync(0xffffffffu, a, o);
          z[i] = a;
        }
        if (lane < 4) {
          const float zz = lane == 0 ? z[0] : lane == 1 ? z[1] : lane == 2 ? z[2] : z[3];
          asm volatile("st.relaxed.gpu.global.f32 [%0], %1;" ::"l"(g_gate + rb * 128 + 16 * j + 4 * w + lane), "f"(tagf(1.0f / (1.0f + __expf(-zz)), tag)) : "memory");
        }
        if (t == 0) PROF_EV(18);
      }
      if (w == 0) {
        const int c = lane >> 4, jj = 16 * blockIdx.x + (lane & 15), jm = (2048 - jj) & 2047;
        const unsigned short* pr = (const unsigned short*)w_r + 256 * c;
        const unsigned short* pi = (const unsigned short*)w_i + 256 * c;
        const float wr = 0.5f * (bf_lo(__ldg(pr + jj * 257)) + bf_lo(__ldg(pr + jm * 257)));
        const float wi = 0.5f * (bf_lo(__ldg(pi + jj * 257)) - bf_lo(__ldg(pi + jm * 257)));
        st_u2(g_Wh + c * 2048 + jj, c ? pack_bf16(-wi, wr) : pack_bf16(wr, wi), tag);
        __syncwarp();
        if (lane == 0) hint_add(&g_cntW[0]);
      }
    };
    if (!helper || w == 0) {
      const int hc = lane >> 4, hj = 16 * (blockIdx.x - 128) + (lane & 15);
      uint32_t u[32];
      if (!helper) {
        const unsigned short* p = (const unsigned short*)(smem + OFF_T) + (t >> 4) * 25 + (t & 15);
        auto w_load = [&](const CUtensorMap* m) {
          if (t == 32) {
            mbar_expect_tx(bars + 8 * B_W, 12288);
#pragma unroll 1
            for (int i = 0; i < 4; i++) { tma4d(sb + OFF_T + i * 3072, m, bars + 8 * B_W, 16 * kg, 0, tn, 8 * i); __nanosleep(WPACE); }
          }
          __syncwarp();
        };
        mbar_wait(bars + 8 * (B_FX + WAFTER), 0);
        if (t == 0) PROF_EV(32);
        w_load(&maps.wr);
        gate_rows();
        mbar_wait(bars + 8 * B_W, 0);
#pragma unroll
        for (int a = 0; a < 32; a++) u[a] = p[a * 192];
        asm volatile("bar.sync 1, 128;" ::: "memory");
        w_load(&maps.wi);
        mbar_wait(bars + 8 * B_W, 1);
#pragma unroll
        for (int a = 0; a < 32; a++) u[a] |= (uint32_t)p[a * 192] << 16;
        asm volatile("bar.sync 1, 128;" ::: "memory");
      } else {
        hint_wait(&g_cntW[0], (ep + 1) * 128u);
        const uint32_t t0 = (uint32_t)clock();
#pragma unroll 1
        for (;;) {
          uint32_t bad = 0;
#pragma unroll
          for (int a = 0; a < 32; a++) { const float2 v = ld_x2((const float2*)g_Wh + hc * 2048 + hj + 64 * a); u[a] = __float_as_uint(v.x); bad |= __float_as_uint(v.y) ^ tag; }
          if (!__any_sync(0xffffffffu, bad & 1)) break;
          spin_guard(t0);
        }
      }
#pragma unroll
      for (int a = 0; a < 32; a++) *(uint32_t*)(smem + OFF_T + (a * 128 + t) * 4) = u[a];
      if (t == 0) PROF_EV(11);
      if (helper) hint_wait(&g_cntX[0], (ep + 1) * 128u); else mbar_wait(bars + 8 * B_HX, 0);
      if (t == 0) PROF_EV(22);
      float2 v[32];
      {
        const int odd = helper ? (lane & 1) : ((t >> 4) & 1);
        const uint32_t* src = (const uint32_t*)(helper ? g_X1s + hc * 32 + (hj >> 1) : g_X1p + (size_t)(kg * 8 + tn) * 2048 + ((t >> 3) & 1) * 32 + w * 8 + (t & 7)) + odd;
        const uint32_t chk = odd ^ 1;
        const uint32_t t0 = (uint32_t)clock();
#pragma unroll 1
        for (;;) {
          uint32_t bad = 0;
#pragma unroll
          for (int a = 0; a < 32; a++) u[a] = ld_x1(src + a * 128);
#pragma unroll
          for (int a = 0; a < 32; a++) bad |= u[a] ^ tag;
          if (!__any_sync(0xffffffffu, bad & chk)) break;
          spin_guard(t0);
        }
#pragma unroll
        for (int a = 0; a < 32; a++) v[a] = make_float2(bf_lo(u[a] & ~chk), bf_hi(u[a]));
      }
      if (t == 0) PROF_EV(12);
#pragma unroll 1
      for (int pass = blockIdx.x >> 16; pass < 2; pass++) {
        dft<-1, 32, 0, 1>(v);
        int go = pass;
        asm volatile("" : "+r"(go));
        if (go == 0) {
#pragma unroll
          for (int a = 0; a < 32; a++) {
            const int b = brev(a, 5);
            if (b < a) continue;
            const uint32_t wa = *(const uint32_t*)(smem + OFF_T + (a * 128 + t) * 4), wb = *(const uint32_t*)(smem + OFF_T + (b * 128 + t) * 4);
            const float2 za = v[b], zb = v[a];
            v[a] = make_float2(fmaf(za.x, bf_hi(wa), za.y * bf_lo(wa)), fmaf(za.x, bf_lo(wa), -za.y * bf_hi(wa)));
            if (b != a) v[b] = make_float2(fmaf(zb.x, bf_hi(wb), zb.y * bf_lo(wb)), fmaf(zb.x, bf_lo(wb), -zb.y * bf_hi(wb)));
          }
        }
      }
      if (t == 0) PROF_EV(16);
      if (!helper) {
        uint2* dst = g_T + (size_t)j * 32768 + (kg & 1) * 1024 + (8 * tn + (t >> 4)) * 16 + (t & 15);
        const bool real_col = kg == 0 && (t & 15) == 0;
#pragma unroll
        for (int a = 0; a < 16; a++) {
          const float2 u0 = v[brev(2 * a, 5)], u1 = v[brev(2 * a + 1, 5)];
          if (!real_col) st_u2(dst + a * 2048, (pack_bf16(u0.y * scale, u0.x * scale) & ~1u) | tag, pack_bf16(u1.y * scale, u1.x * scale));
          if (TPACE && (a & 3) == 3 && a < 15) __nanosleep(TPACE);
        }
        __syncwarp();
        if (lane == 0) hint_add(&g_cntT[32 * j]);
        if (t == 0) PROF_EV(17);
        const uint4* src = (const uint4*)(g_T + (size_t)(j * 16 + rb) * 2048) + t;
        uint4 tv[8];
        mbar_wait(bars + 8 * B_HT, 0);
        if (t == 0) PROF_EV(23);
        const uint32_t t0 = (uint32_t)clock();
#pragma unroll 1
        for (;;) {
          uint32_t bad = 0;
#pragma unroll
          for (int a = 0; a < 8; a++) tv[a] = ld_x4(src + a * 128);
#pragma unroll
          for (int a = 0; a < 8; a++) bad |= (tv[a].x ^ tag) | (tv[a].z ^ tag);
          if (!__any_sync(0xffffffffu, bad & 1)) break;
          spin_guard(t0);
        }
        const int r = t >> 3, c = t & 7;
#pragma unroll
        for (int a = 0; a < 8; a++) {
          const uint32_t dst2 = sb + OFF_T + (16 * (a & 3) + r) * 128 + ((((a >> 2) * 4 + (c >> 1)) ^ (r & 7)) << 4) + (c & 1) * 8;
          asm volatile("st.shared.v2.u32 [%0], {%1,%2};" ::"r"(dst2), "r"(tv[a].x & ~1u), "r"(tv[a].z & ~1u) : "memory");
          asm volatile("st.shared.v2.u32 [%0], {%1,%2};" ::"r"(dst2 + 8192), "r"(tv[a].y), "r"(tv[a].w) : "memory");
        }
        asm volatile("fence.proxy.async.shared::cta;" ::: "memory");
        __syncwarp();
        if (lane == 0) mbar_arrive(bars + 8 * B_T);
        if (t == 0) PROF_EV(13);
      } else {
#pragma unroll
        for (int a = 0; a < 8; a++) {
          uint32_t pk[2];
#pragma unroll
          for (int e = 0; e < 2; e++) {
            const float2 u0 = v[brev(4 * a + e, 5)], u1 = v[brev(4 * a + 2 + e, 5)];
            const float2 keep = hc ? u1 : u0, give = hc ? u0 : u1;
            const float ox = __shfl_xor_sync(0xffffffffu, give.x, 16), oy = __shfl_xor_sync(0xffffffffu, give.y, 16);
            pk[e] = pack_bf16((keep.y + oy) * (0.5f * scale), (keep.x + ox) * (0.5f * scale));
          }
          st_u2(g_T + (2 * a + hc) * 2048 + hj * 16, (pk[0] & ~1u) | tag, pk[1]);
        }
        __syncwarp();
        if (t == 0) { hint_add(&g_cntT[0]); g_epoch[blockIdx.x * 8] = ep + 1; PROF_EV(13); }
      }
    }
  } else {
    asm volatile("setmaxnreg.inc.sync.aligned.u32 200;");
    if (!helper) {
      const int wg = warp >> 2, w = warp & 3, g = lane >> 2, q = lane & 3;
      const bool elect = (tid & 127) == 0;
      const uint32_t ep = ld_x1(&g_epoch[blockIdx.x * 8]);
      float c1[64], cA[64], c2[64], ci[64], ct[64];
      const int zero = blockIdx.x >> 16;
      uint32_t h[56], yf[16];
      const uint32_t d0 = (sb & 0x3FFFF) >> 4;
      const uint32_t dK = d0 | (1u << 16), dN = d0 | (512u << 16), dM = d0 | (256u << 16);
      const uint32_t dX = dK + wg * 512;
      constexpr uint32_t RING = OFF_RING >> 4;
      auto waitA = [&](int n) { mbar_wait(bars + 8 * (B_FA + rslot(n)), rpar(n)); };
      auto freeA = [&](int n) { if (elect) mbar_arrive(bars + 8 * (B_EA + rslot(n))); };
      auto nop = [](int) {};

#pragma unroll
      for (int kb = 0; kb < 8; kb++) {
        if (kb < NEARLY) {
          if (NEARLY - 1 - kb == 3) asm volatile("cp.async.wait_group 3;" ::: "memory");
          else if (NEARLY - 1 - kb == 2) asm volatile("cp.async.wait_group 2;" ::: "memory");
          else if (NEARLY - 1 - kb == 1) asm volatile("cp.async.wait_group 1;" ::: "memory");
          else asm volatile("cp.async.wait_group 0;" ::: "memory");
          asm volatile("fence.proxy.async.shared::cta;" ::: "memory");
          if (kb == 0) asm volatile("bar.sync 0, 512;" ::: "memory");
          else asm volatile("bar.sync 2, 256;" ::: "memory");
        } else {
          mbar_wait(bars + 8 * (B_FX + kb), 0); waitA(kb);
        }
        wg_fence();
        const uint64_t dx = d128(dX + kb * 1024), df = d128(dK + RING + rslot(kb) * 1024), dm = d64(dM + RING + 512 + rslot(kb) * 1024);
        if (kb == 0) { mma_ss64<0, 0, 0>(c1, df, dx); mma_ss64<32, 1, 0>(c1, dx, dm); }
        else { mma_ss64<0, 0, 1>(c1, df, dx); mma_ss64<32, 1, 1>(c1, dx, dm); wg_commit(); wg_wait<1>(); freeA(kb - 1); }
#pragma unroll
        for (int k = 1; k < 4; k++) {
          mma_ss64<0, 0, 1>(c1, df + k * 2, dx + k * 2);
          mma_ss64<32, 1, 1>(c1, dx + k * 2, dm + k * 64);
        }
        wg_commit();
        if (kb == 0 && tid == 0) PROF_EV(1);
      }
      auto ffn_step = [&](auto first, float (&acc)[64], int n, int kb, auto done, auto work) {
        waitA(n);
        wg_fence();
        const uint64_t dx = d128(dX + kb * 1024), db = d128(dN + RING + rslot(n) * 1024);
        mma_ss128<0, 1, decltype(first)::value>(acc, dx, db, zero);
        wg_commit();
        wg_wait<1>();
        done();
#pragma unroll
        for (int k = 1; k < 4; k++) { mma_ss128<0, 1, 1>(acc, dx + k * 2, db + k * 128); work(k - 1); }
        wg_commit();
        work(3);
      };
      const uint32_t tag = (ep + 1) & 1;
      float hm[16];
      ffn_step(IC<0>(), c2, 8, 0, [&] { freeA(7); fence_regs<0, 64>(c1); }, [&](int i) {
#pragma unroll
        for (int e = 4 * i; e < 4 * i + 4; e++) { yf[e] = pack_pin(c1[2 * e], c1[2 * e + 1]); hm[e] = fmaxf(c1[32 + e], 0.f) * c1[48 + e]; }
      });
      fence_regs<0, 16>(hm);
      if (tid == 0) PROF_EV(2);
      {
        waitA(9); waitA(10);
        const uint64_t de = d128(dN + RING + (wg ? rslot(10) : rslot(9)) * 1024);
        wg_fence();
        mma_rs128<0, 1, 0>(cA, yf[0], yf[1], yf[2], yf[3], de);
        wg_commit();
        wg_wait<1>();
        freeA(8);
#pragma unroll
        for (int k = 1; k < 4; k++) mma_rs128<0, 1, 1>(cA, yf[4 * k], yf[4 * k + 1], yf[4 * k + 2], yf[4 * k + 3], de + k * 128);
        wg_commit();
      }
      {
        const int s0 = 2 * rb + wg;
        uint2* dst = g_X1p + ((size_t)((2 * j + (w >> 1)) * 8) * 32 + s0) * 64 + (w & 1) * 32 + q * 8 + g;
        auto x1_store = [&](int n) {
          st_u2(dst + n * 2048, (pack_bf16(cA[4 * n] - cA[34 + 4 * n], cA[32 + 4 * n] + cA[4 * n + 2]) & ~1u) | tag,
                pack_bf16(cA[4 * n + 1] - cA[35 + 4 * n], cA[33 + 4 * n] + cA[4 * n + 3]));
        };
        ffn_step(IC<1>(), c2, 11, 1, [&] { freeA(9); freeA(10); fence_regs<0, 64>(cA); }, [&](int i) { x1_store(i); });
        if (tid == 0) PROF_EV(19);
        ffn_step(IC<1>(), c2, 12, 2, [&] { freeA(11); }, [&](int i) { x1_store(4 + i); });
        if (j == 0 && w == 0 && g == 0) {
#pragma unroll
          for (int n = 0; n < 8; n++) {
            st_u2(g_X1s + s0 * 64 + 4 * n + q, (pack_bf16(cA[4 * n], cA[32 + 4 * n]) & ~1u) | tag, pack_bf16(cA[4 * n + 1], cA[33 + 4 * n]));
            st_u2(g_X1s + s0 * 64 + 32 + 4 * n + q, (pack_bf16(cA[4 * n + 2], cA[34 + 4 * n]) & ~1u) | tag, pack_bf16(cA[4 * n + 3], cA[35 + 4 * n]));
          }
        }
        __syncwarp();
        if (lane == 0) hint_add(&g_cntX[32 * j]);
        if (tid == 0) PROF_EV(3);
      }
      const float* gp = g_gate + rb * 128 + wg * 64 + w * 16 + g;
      uint32_t gb0 = ld_x1(gp), gb1 = ld_x1(gp + 8);
#pragma unroll
      for (int kb = 3; kb < 7; kb++) ffn_step(IC<1>(), c2, 10 + kb, kb, [&] { freeA(9 + kb); }, nop);
      {
        const uint32_t t0 = (uint32_t)clock();
        while (__any_sync(0xffffffffu, ((gb0 ^ tag) | (gb1 ^ tag)) & 1)) { gb0 = ld_x1(gp); gb1 = ld_x1(gp + 8); spin_guard(t0); }
      }
      const float g0 = __uint_as_float(gb0 & ~1u), g1 = __uint_as_float(gb1 & ~1u);
      const float o0 = 1.0f - g0, o1 = 1.0f - g1;
      ffn_step(IC<1>(), c2, 17, 7, [&] { freeA(16); }, [&](int i) {
        h[48 + 2 * i] = pack_pin(hm[4 * i] * o0, hm[4 * i + 1] * o0); h[49 + 2 * i] = pack_pin(hm[4 * i + 2] * o1, hm[4 * i + 3] * o1);
      });
      auto glu = [&](float (&acc)[64], int ho, int i0, int i1) {
#pragma unroll
        for (int i = i0; i < i1; i++) {
          const float o = (i & 1) ? o1 : o0;
          h[ho + i] = pack_pin(fmaxf(acc[2 * i], 0.f) * acc[32 + 2 * i] * o, fmaxf(acc[2 * i + 1], 0.f) * acc[33 + 2 * i] * o);
        }
      };
      ffn_step(IC<2>(), cA, 18, 0, [&] { freeA(17); fence_regs<0, 64>(c2); }, [&](int i) { glu(c2, 0, 2 * i, 2 * i + 2); });
      if (tid == 0) PROF_EV(4);
      ffn_step(IC<1>(), cA, 19, 1, [&] { freeA(18); }, [&](int i) { glu(c2, 0, 8 + 2 * i, 10 + 2 * i); });
#pragma unroll
      for (int kb = 2; kb < 8; kb++) ffn_step(IC<1>(), cA, 18 + kb, kb, [&] { freeA(17 + kb); }, nop);
      ffn_step(IC<2>(), c2, 26, 0, [&] { freeA(25); fence_regs<0, 64>(cA); }, [&](int i) { glu(cA, 16, 2 * i, 2 * i + 2); });
      if (tid == 0) PROF_EV(5);
      ffn_step(IC<1>(), c2, 27, 1, [&] { freeA(26); }, [&](int i) { glu(cA, 16, 8 + 2 * i, 10 + 2 * i); });
#pragma unroll
      for (int kb = 2; kb < 8; kb++)
        ffn_step(IC<1>(), c2, 26 + kb, kb, [&] {
          if (kb < 6) freeA(25 + kb);
          if (kb >= 3 && (kb & 1) && elect) mbar_arrive(bars + 8 * (B_ET + ((kb - 3) >> 1)));
        }, nop);
      wg_wait<0>();
      if (elect) mbar_arrive(bars + 8 * (B_ET + 3));
      fence_regs<0, 64>(c2);
      glu(c2, 32, 0, 16);
      if (wg) waitA(35); else waitA(34);
      if (tid == 0) PROF_EV(6);
      mbar_wait(bars + 8 * B_T, 0);
      if (tid == 0) PROF_EV(7);
      wg_fence();
      {
        const uint64_t dt = d128(dN + (OFF_T >> 4) + wg * 512), de = d128(dK + RING + (wg ? rslot(35) : rslot(34)) * 1024);
        mma_ss64<0, 1, 0>(ci, de, dt);
        mma_ss64<32, 1, 0>(ci, de + 512, dt);
#pragma unroll
        for (int k = 1; k < 4; k++) {
          mma_ss64<0, 1, 1>(ci, de + k * 2, dt + k * 128);
          mma_ss64<32, 1, 1>(ci, de + (512 + k * 2), dt + k * 128);
        }
      }
      wg_commit();

      auto head = [&](auto off, int t) {
        constexpr int O = decltype(off)::value;
        mbar_wait(bars + 8 * (B_FT + (t & 3)), t >> 2);
        const uint64_t db = d128(dN + (t & 3) * (TB >> 4));
        wg_fence();
        mma_rs64<O, 1, 0>(ct, h[0], h[1], h[2], h[3], db);
#pragma unroll
        for (int k = 1; k < 6; k++) mma_rs64<O, 1, 1>(ct, h[4 * k], h[4 * k + 1], h[4 * k + 2], h[4 * k + 3], db + k * 128);
        wg_commit();
        wg_wait<1>();
      };
      auto rest = [&](auto off, int t) {
        constexpr int O = decltype(off)::value;
        const uint64_t db = d128(dN + (t & 3) * (TB >> 4));
        wg_fence();
#pragma unroll
        for (int k = 6; k < 14; k++) mma_rs64<O, 1, 1>(ct, h[4 * k], h[4 * k + 1], h[4 * k + 2], h[4 * k + 3], db + k * 128);
#pragma unroll
        for (int k = 0; k < 4; k++) mma_rs64<O, 1, 1>(ct, yf[4 * k], yf[4 * k + 1], yf[4 * k + 2], yf[4 * k + 3], db + (14 + k) * 128);
        wg_commit();
      };
      auto freeT = [&](int t) { if (elect) mbar_arrive(bars + 8 * (B_ET + t)); };
      const uint32_t peerZ = mapa(sb + OFF_Z + tid * 16, rank ^ 1), peerB = mapa(bars + 8 * B_Z, rank ^ 1);
      auto send_peer = [&](auto off, int z) {
        constexpr int O = decltype(off)::value;
        fence_regs<O, 32>(ct);
#pragma unroll
        for (int i = 0; i < 4; i++)
          asm volatile("st.async.weak.shared::cluster.mbarrier::complete_tx::bytes.v4.b32 [%0], {%1,%2,%3,%4}, [%5];" ::"r"(peerZ + z * U + i * 4096),
                       "r"(pack_bf16(ct[O + 8 * i], ct[O + 8 * i + 1])), "r"(pack_bf16(ct[O + 8 * i + 2], ct[O + 8 * i + 3])),
                       "r"(pack_bf16(ct[O + 8 * i + 4], ct[O + 8 * i + 5])), "r"(pack_bf16(ct[O + 8 * i + 6], ct[O + 8 * i + 7])), "r"(peerB + 8 * z) : "memory");
      };
      auto send_grid = [&](auto off, int z) {
        constexpr int O = decltype(off)::value;
        fence_regs<O, 32>(ct);
        mbar_wait(bars + 8 * (B_Z + z), 0);
        uint4* dst = g_part + (size_t)((rb * 8 + 2 * ((q4 + z + 1) & 3) + rank) * 3 + z) * 1024 + tid;
#pragma unroll
        for (int i = 0; i < 4; i++) {
          const uint4 p = *(const uint4*)(smem + OFF_Z + z * U + i * 4096 + tid * 16);
          st_x4(dst + i * 256, (pack_bf16(ct[O + 8 * i] + bf_lo(p.x), ct[O + 8 * i + 1] + bf_hi(p.x)) & ~1u) | tag,
                pack_bf16(ct[O + 8 * i + 2] + bf_lo(p.y), ct[O + 8 * i + 3] + bf_hi(p.y)),
                pack_bf16(ct[O + 8 * i + 4] + bf_lo(p.z), ct[O + 8 * i + 5] + bf_hi(p.z)),
                pack_bf16(ct[O + 8 * i + 6] + bf_lo(p.w), ct[O + 8 * i + 7] + bf_hi(p.w)));
        }
        __syncwarp();
        if (lane == 0) hint_add(&g_cntP[32 * (rb * 8 + 2 * ((q4 + z + 1) & 3) + rank) + z]);
      };
      asm volatile("barrier.cluster.wait.aligned;" ::: "memory");
      head(IC<0>(), 0);
      if (elect) asm volatile("mbarrier.arrive.shared::cluster.b64 _, [%0];" ::"r"(mapa(bars + 8 * B_RDY, rank ^ 1)) : "memory");
      fence_regs<0, 64>(ci);
#pragma unroll
      for (int i = 0; i < 16; i++) {
        const float gg = (i & 1) ? g1 : g0;
        yf[i] = pack_pin((ci[2 * i] + ci[33 + 2 * i]) * gg, (ci[2 * i + 1] - ci[32 + 2 * i]) * gg);
      }
      rest(IC<0>(), 0);
      if (tid == 0) PROF_EV(8);
      head(IC<32>(), 1); freeT(0); mbar_wait(bars + 8 * B_RDY, 0); send_peer(IC<0>(), 0); rest(IC<32>(), 1);
      head(IC<0>(), 2); freeT(1); send_peer(IC<32>(), 1); rest(IC<0>(), 2);
      head(IC<32>(), 3); freeT(2); send_peer(IC<0>(), 2); rest(IC<32>(), 3);
      head(IC<0>(), 4); freeT(3); send_grid(IC<32>(), 0); rest(IC<0>(), 4);
      head(IC<32>(), 5); send_grid(IC<0>(), 1); rest(IC<32>(), 5);
      head(IC<0>(), 6); send_grid(IC<32>(), 2); rest(IC<0>(), 6);
      head(IC<32>(), 7); send_peer(IC<0>(), 3);
      {
        const uint4* src = g_part + (size_t)(rb * 8 + j) * 3 * 1024 + tid;
        uint4 pv[12];
        mbar_wait(bars + 8 * (B_HP + 1), 0);
#pragma unroll
        for (int i = 0; i < 8; i++) pv[i] = ld_x4(src + i * 256);
        rest(IC<32>(), 7);
        if (tid == 0) PROF_EV(9);
        mbar_wait(bars + 8 * (B_HP + 2), 0);
        if (tid == 0) PROF_EV(24);
#pragma unroll
        for (int i = 8; i < 12; i++) pv[i] = ld_x4(src + i * 256);
        const uint32_t t0 = (uint32_t)clock();
        for (;;) {
          uint32_t bad = 0;
#pragma unroll
          for (int i = 0; i < 12; i++) bad |= pv[i].x ^ tag;
          if (!__any_sync(0xffffffffu, bad & 1)) break;
#pragma unroll
          for (int i = 0; i < 12; i++) pv[i] = ld_x4(src + i * 256);
          spin_guard(t0);
        }
        if (tid == 0) PROF_EV(14);
        float sum[32];
#pragma unroll
        for (int i = 0; i < 4; i++) {
          const uint32_t a[4] = {pv[i].x & ~1u, pv[i].y, pv[i].z, pv[i].w}, b[4] = {pv[4 + i].x & ~1u, pv[4 + i].y, pv[4 + i].z, pv[4 + i].w},
                         c[4] = {pv[8 + i].x & ~1u, pv[8 + i].y, pv[8 + i].z, pv[8 + i].w};
#pragma unroll
          for (int e = 0; e < 4; e++) {
            sum[8 * i + 2 * e] = bf_lo(a[e]) + bf_lo(b[e]) + bf_lo(c[e]);
            sum[8 * i + 2 * e + 1] = bf_hi(a[e]) + bf_hi(b[e]) + bf_hi(c[e]);
          }
        }
        mbar_wait(bars + 8 * (B_Z + 3), 0);
#pragma unroll
        for (int i = 0; i < 4; i++) {
          const uint4 p = *(const uint4*)(smem + OFF_Z + 3 * U + i * 4096 + tid * 16);
          const uint32_t a[4] = {p.x, p.y, p.z, p.w};
#pragma unroll
          for (int e = 0; e < 4; e++) { sum[8 * i + 2 * e] += bf_lo(a[e]); sum[8 * i + 2 * e + 1] += bf_hi(a[e]); }
        }
        wg_wait<0>();
        fence_regs<32, 32>(ct);
#pragma unroll
        for (int i = 0; i < 32; i++) sum[i] += ct[32 + i];
        const uint32_t stg = sb + OFF_T + warp * 2048;
        const int mr = (lane & 7) + ((lane >> 3) & 1) * 8, mc = lane >> 4;
#pragma unroll
        for (int i = 0; i < 4; i++) {
          const uint32_t a = stg + mr * 128 + (((2 * i + mc) ^ (mr & 7)) << 4);
          asm volatile("stmatrix.sync.aligned.m8n8.x4.shared.b16 [%0], {%1,%2,%3,%4};" ::"r"(a), "r"(pack_bf16(sum[8 * i], sum[8 * i + 1])),
                       "r"(pack_bf16(sum[8 * i + 2], sum[8 * i + 3])), "r"(pack_bf16(sum[8 * i + 4], sum[8 * i + 5])),
                       "r"(pack_bf16(sum[8 * i + 6], sum[8 * i + 7])) : "memory");
        }
        __syncwarp();
#pragma unroll
        for (int i = 0; i < 4; i++) {
          const int r = 4 * i + (lane >> 3), c = lane & 7;
          const uint4 v = *(const uint4*)(smem + OFF_T + warp * 2048 + r * 128 + ((c ^ (r & 7)) << 4));
          *(uint4*)(out + (size_t)(2 * rb + wg + 32 * (16 * w + r)) * 512 + 64 * j + 8 * c) = v;
        }
      }
      if (tid == 0) { g_epoch[blockIdx.x * 8] = ep + 1; PROF_EV(15); PROF_CK(41); }
    }
  }
}

typedef CUresult (*EncodeFn)(CUtensorMap*, CUtensorMapDataType, cuuint32_t, void*, const cuuint64_t*, const cuuint64_t*, const cuuint32_t*,
                             const cuuint32_t*, CUtensorMapInterleave, CUtensorMapSwizzle, CUtensorMapL2promotion, CUtensorMapFloatOOBfill);

static void encode(EncodeFn f, CUtensorMap* m, const void* base, int rank, const cuuint64_t* dims, const cuuint64_t* strides, const cuuint32_t* box,
                   CUtensorMapSwizzle sw) {
  cuuint32_t es[5] = {1, 1, 1, 1, 1};
  f(m, CU_TENSOR_MAP_DATA_TYPE_BFLOAT16, rank, (void*)base, dims, strides, box, es, CU_TENSOR_MAP_INTERLEAVE_NONE, sw,
    CU_TENSOR_MAP_L2_PROMOTION_L2_128B, CU_TENSOR_MAP_FLOAT_OOB_FILL_NONE);
}

extern "C" void kernel_launch(void* const* d_in, const int* in_sizes, int n_in, void* d_out, int out_size) {
  (void)in_sizes; (void)n_in; (void)out_size;
  const __nv_bfloat16* x = (const __nv_bfloat16*)d_in[0];
  const __nv_bfloat16* w_r = (const __nv_bfloat16*)d_in[1];
  const __nv_bfloat16* w_i = (const __nv_bfloat16*)d_in[2];
  const __nv_bfloat16* Wg = (const __nv_bfloat16*)d_in[4];
  const __nv_bfloat16* Wu = (const __nv_bfloat16*)d_in[5];
  const __nv_bfloat16* Wd = (const __nv_bfloat16*)d_in[6];
  const __nv_bfloat16* gw = (const __nv_bfloat16*)d_in[7];

  void* fp = nullptr; cudaDriverEntryPointQueryResult qr;
  cudaGetDriverEntryPoint("cuTensorMapEncodeTiled", &fp, cudaEnableDefault, &qr);
  EncodeFn enc = (EncodeFn)fp;
  void *pFT, *pET;
  cudaGetSymbolAddress(&pFT, g_FT); cudaGetSymbolAddress(&pET, g_ET);

  Maps mp;
  const CUtensorMapSwizzle S128 = CU_TENSOR_MAP_SWIZZLE_128B, S64 = CU_TENSOR_MAP_SWIZZLE_64B;
  { cuuint64_t d[3] = {512, 64, 32}, s[2] = {32768, 1024}; cuuint32_t b[3] = {64, 64, 2}; encode(enc, &mp.x, x, 3, d, s, b, S128); }
  { cuuint64_t d[2] = {512, 512}, s[1] = {1024}; cuuint32_t b[2] = {64, 64}; encode(enc, &mp.ft, pFT, 2, d, s, b, S128); }
  { cuuint64_t d[4] = {512, 2, 8, 32}, s[3] = {8192, 1024, 16384}; cuuint32_t b[4] = {64, 2, 8, 4}; encode(enc, &mp.fg, pFT, 4, d, s, b, S128); }
  { cuuint64_t d[4] = {64, 64, 2, 32}, s[3] = {8192, 128, 256}; cuuint32_t b[4] = {64, 64, 2, 1}; encode(enc, &mp.e, pET, 4, d, s, b, S128); }
  { cuuint64_t d[2] = {1792, 512}, s[1] = {3584}; cuuint32_t b[2] = {64, 64}, b2[2] = {32, 64};
    encode(enc, &mp.g64, Wg, 2, d, s, b, S128); encode(enc, &mp.u64, Wu, 2, d, s, b, S128);
    encode(enc, &mp.g32, Wg, 2, d, s, b2, S64); encode(enc, &mp.u32, Wu, 2, d, s, b2, S64); }
  { cuuint64_t d[2] = {512, 1792}, s[1] = {1024}; cuuint32_t b[2] = {64, 192}, b2[2] = {64, 32};
    encode(enc, &mp.d192, Wd, 2, d, s, b, S128); encode(enc, &mp.d32, Wd, 2, d, s, b2, S128); }

  { cuuint64_t d[4] = {264, 8, 8, 32}, s[3] = {512, 4112, 32896}; cuuint32_t b[4] = {24, 8, 1, 8};
    encode(enc, &mp.wr, w_r, 4, d, s, b, CU_TENSOR_MAP_SWIZZLE_NONE); encode(enc, &mp.wi, w_i, 4, d, s, b, CU_TENSOR_MAP_SWIZZLE_NONE); }

  cudaFuncSetAttribute(fused_kernel, cudaFuncAttributeMaxDynamicSharedMemorySize, SMEM_BYTES);
  fused_kernel<<<NCTA, 512, SMEM_BYTES>>>(mp, x, w_r, w_i, gw, Wg, Wu, (__nv_bfloat16*)d_out);
}
```

```cpp
#include <cuda_runtime.h>
#include <cuda_bf16.h>
#include <cuda.h>
#include <stdint.h>

namespace tbl {
constexpr double PI = 3.14159265358979323846264338327950288;
constexpr double sin_s(double x) { double t = x, s = x; for (int n = 1; n < 12; n++) { t *= -x * x / ((2 * n) * (2 * n + 1)); s += t; } return s; }
constexpr double cos_s(double x) { double t = 1, s = 1; for (int n = 1; n < 12; n++) { t *= -x * x / ((2 * n - 1) * (2 * n)); s += t; } return s; }
constexpr double cos2048(int m) {
  m &= 2047; if (m > 1024) m = 2048 - m;
  bool neg = false; if (m > 512) { m = 1024 - m; neg = true; }
  double v = (m <= 256) ? cos_s(2 * PI * m / 2048) : sin_s(2 * PI * (512 - m) / 2048);
  return neg ? -v : v;
}
constexpr uint16_t to_bf16(double v) {
  if (v == 0) return 0;
  uint16_t s = 0; if (v < 0) { s = 0x8000; v = -v; }
  int e = 0; while (v >= 2) { v /= 2; e++; } while (v < 1) { v *= 2; e--; }
  double m = (v - 1) * 128; int mi = (int)m; double fr = m - mi;
  if (fr > 0.5 || (fr == 0.5 && (mi & 1))) mi++;
  if (mi == 128) { mi = 0; e++; }
  return (uint16_t)(s | ((e + 127) << 7) | mi);
}
struct CosT { uint16_t v[2048]; constexpr CosT() : v() { for (int i = 0; i < 2048; i++) v[i] = to_bf16(cos2048(i)); } };
struct alignas(1024) FT {
  uint16_t v[512 * 512];
  constexpr FT() : v() {
    CosT c;
    for (int r = 0; r < 512; r++) {
      int k = (r >> 4) * 8 + (r & 7), e = (r >> 3) & 1;
      int mul = 4 * k, add = e ? 512 : 0;
      if (k == 0 && e == 1) { mul = 1024; add = 0; }
      for (int d = 0; d < 512; d++) v[r * 512 + d] = c.v[(d * mul + add) & 2047];
    }
  }
};
struct alignas(1024) ET {
  uint16_t v[2048 * 128];
  constexpr ET() : v() {
    CosT c;
    for (int s = 0; s < 2048; s++)
      for (int j = 0; j < 64; j++) { v[s * 128 + j] = c.v[(s * j) & 2047]; v[s * 128 + 64 + j] = c.v[(s * j + 512) & 2047]; }
  }
};
struct alignas(1024) DT {
  uint16_t v[64 * 64];
  constexpr DT() : v() {
    CosT c;
    for (int r = 0; r < 64; r++)
      for (int n = 0; n < 64; n++) {
        const int sg = r >> 1, s0 = (sg & ~7) + 2 * (sg & 3) + ((sg >> 2) & 1), e = r & 1, f = n & 1;
        const int m = 64 * s0 * (n >> 1) + (e == f ? 0 : e ? -512 : 512);
        v[r * 64 + (((n >> 3) ^ (r & 7)) << 3) + (n & 7)] = c.v[m & 2047];
      }
  }
};
}

__device__ constexpr tbl::FT g_FT = tbl::FT();
__device__ constexpr tbl::ET g_ET = tbl::ET();
__device__ constexpr tbl::DT g_DT = tbl::DT();

__device__ __align__(1024) uint2 g_X1p[129 * 32 * 64];
__device__ __align__(1024) uint2 g_T[8 * 16 * 2 * 64 * 16];
__device__ __align__(1024) uint4 g_part[128 * 3 * 1024];
__device__ __align__(16) float g_gate[16 * 128];
__device__ __align__(16) uint2 g_Wh[2 * 2048];
__device__ unsigned g_epoch[132 * 8];
__device__ unsigned g_cntX[8 * 32], g_cntT[8 * 32], g_cntP[128 * 32], g_cntW[32];
#define PROF_EV(i) do {} while (0)
#define PROF_CK(i) do {} while (0)

__device__ __forceinline__ uint32_t smem_u32(const void* p) { return (uint32_t)__cvta_generic_to_shared(p); }
__device__ __forceinline__ void mbar_init(uint32_t bar, uint32_t cnt) { asm volatile("mbarrier.init.shared::cta.b64 [%0], %1;" ::"r"(bar), "r"(cnt)); }
__device__ __forceinline__ void mbar_expect_tx(uint32_t bar, uint32_t bytes) { asm volatile("mbarrier.arrive.expect_tx.shared::cta.b64 _, [%0], %1;" ::"r"(bar), "r"(bytes) : "memory"); }
__device__ __forceinline__ void mbar_arrive(uint32_t bar) { asm volatile("mbarrier.arrive.shared::cta.b64 _, [%0];" ::"r"(bar) : "memory"); }
__device__ __forceinline__ void mbar_wait(uint32_t bar, uint32_t parity) {
  asm volatile(
      "{\n.reg .pred p;\n.reg .u32 n;\nmov.u32 n, 0;\n"
      "W_LOOP:\nmbarrier.try_wait.parity.shared::cta.b64 p, [%0], %1;\n@p bra W_DONE;\n"
      "add.u32 n, n, 1;\nsetp.lt.u32 p, n, 0x40000;\n@p bra W_LOOP;\ntrap;\nW_DONE:\n}" ::"r"(bar), "r"(parity) : "memory");
}
__device__ __forceinline__ void bulk_load(uint32_t dst, const void* src, uint32_t bytes, uint32_t bar) {
  asm volatile("cp.async.bulk.shared::cluster.global.mbarrier::complete_tx::bytes [%0], [%1], %2, [%3];" ::"r"(dst), "l"(src), "r"(bytes), "r"(bar) : "memory");
}
__device__ __forceinline__ void cp16(uint32_t dst, const void* src) { asm volatile("cp.async.cg.shared.global [%0], [%1], 16;" ::"r"(dst), "l"(src) : "memory"); }
__device__ __forceinline__ void spin_guard(uint32_t t0) { if ((uint32_t)clock() - t0 > (1u << 30)) __trap(); }
__device__ __forceinline__ float tagf(float v, uint32_t tag) { return __uint_as_float((__float_as_uint(v) & ~1u) | tag); }
__device__ __forceinline__ float untag(float v) { return __uint_as_float(__float_as_uint(v) & ~1u); }
__device__ __forceinline__ void st_x2(float2* p, float a, float b) { asm volatile("st.relaxed.gpu.global.v2.f32 [%0], {%1,%2};" ::"l"(p), "f"(a), "f"(b) : "memory"); }
__device__ __forceinline__ float2 ld_x2(const float2* p) { float2 v; asm volatile("ld.relaxed.gpu.global.v2.f32 {%0,%1}, [%2];" : "=f"(v.x), "=f"(v.y) : "l"(p) : "memory"); return v; }
__device__ __forceinline__ void st_u2(uint2* p, uint32_t a, uint32_t b) { asm volatile("st.relaxed.gpu.global.v2.u32 [%0], {%1,%2};" ::"l"(p), "r"(a), "r"(b) : "memory"); }
__device__ __forceinline__ void prefetch2d(const CUtensorMap* m, int c0, int c1) { asm volatile("cp.async.bulk.prefetch.tensor.2d.L2.global [%0, {%1, %2}];" ::"l"(m), "r"(c0), "r"(c1) : "memory"); }
__device__ __forceinline__ void prefetch1d(const void* p, uint32_t bytes) { asm volatile("cp.async.bulk.prefetch.L2.global [%0], %1;" ::"l"(p), "r"(bytes) : "memory"); }
__device__ __forceinline__ uint32_t ld_x1(const void* p) { uint32_t v; asm volatile("ld.relaxed.gpu.global.u32 %0, [%1];" : "=r"(v) : "l"(p) : "memory"); return v; }
__device__ __forceinline__ uint4 ld_x4(const void* p) { uint4 v; asm volatile("ld.relaxed.gpu.global.v4.u32 {%0,%1,%2,%3}, [%4];" : "=r"(v.x), "=r"(v.y), "=r"(v.z), "=r"(v.w) : "l"(p) : "memory"); return v; }
__device__ __forceinline__ void st_x4(void* p, uint32_t a, uint32_t b, uint32_t c, uint32_t d) { asm volatile("st.relaxed.gpu.global.v4.u32 [%0], {%1,%2,%3,%4};" ::"l"(p), "r"(a), "r"(b), "r"(c), "r"(d) : "memory"); }
__device__ __forceinline__ uint32_t mapa(uint32_t a, uint32_t cta) { uint32_t r; asm volatile("mapa.shared::cluster.u32 %0, %1, %2;" : "=r"(r) : "r"(a), "r"(cta)); return r; }
__device__ __forceinline__ void hint_add(unsigned* p) { asm volatile("red.relaxed.gpu.global.add.u32 [%0], 1;" ::"l"(p) : "memory"); }
__device__ __forceinline__ void hint_wait(const unsigned* p, unsigned target) {
  const uint32_t t0 = (uint32_t)clock();
  while ((int)(ld_x1(p) - target) < 0) spin_guard(t0);
}
__device__ __forceinline__ void tma2d(uint32_t dst, const CUtensorMap* m, uint32_t bar, int c0, int c1) {
  asm volatile("cp.async.bulk.tensor.2d.shared::cluster.global.mbarrier::complete_tx::bytes [%0], [%1, {%3, %4}], [%2];" ::"r"(dst), "l"(m), "r"(bar), "r"(c0), "r"(c1) : "memory");
}
__device__ __forceinline__ void tma3d(uint32_t dst, const CUtensorMap* m, uint32_t bar, int c0, int c1, int c2) {
  asm volatile("cp.async.bulk.tensor.3d.shared::cluster.global.mbarrier::complete_tx::bytes [%0], [%1, {%3, %4, %5}], [%2];" ::"r"(dst), "l"(m), "r"(bar), "r"(c0), "r"(c1), "r"(c2) : "memory");
}
__device__ __forceinline__ void tma4d(uint32_t dst, const CUtensorMap* m, uint32_t bar, int c0, int c1, int c2, int c3) {
  asm volatile("cp.async.bulk.tensor.4d.shared::cluster.global.mbarrier::complete_tx::bytes [%0], [%1, {%3, %4, %5, %6}], [%2];" ::"r"(dst), "l"(m), "r"(bar), "r"(c0), "r"(c1), "r"(c2), "r"(c3) : "memory");
}
__device__ __forceinline__ void wg_fence() { asm volatile("wgmma.fence.sync.aligned;" ::: "memory"); }
__device__ __forceinline__ void wg_commit() { asm volatile("wgmma.commit_group.sync.aligned;" ::: "memory"); }
template <int N> __device__ __forceinline__ void wg_wait() { asm volatile("wgmma.wait_group.sync.aligned %0;" ::"n"(N) : "memory"); }
template <int O, int N, int NN> __device__ __forceinline__ void fence_regs(float (&d)[NN]) {
#pragma unroll
  for (int i = 0; i < N; i++) asm volatile("" : "+f"(d[O + i])::"memory");
}
__device__ __forceinline__ uint32_t pack_bf16(float lo, float hi) {
  uint32_t r; asm("cvt.rn.bf16x2.f32 %0, %1, %2;" : "=r"(r) : "f"(hi), "f"(lo)); return r;
}
__device__ __forceinline__ uint32_t pack_pin(float lo, float hi) {
  uint32_t r; asm volatile("cvt.rn.bf16x2.f32 %0, %1, %2;" : "=r"(r) : "f"(hi), "f"(lo) : "memory"); return r;
}
__device__ __forceinline__ float bf_lo(uint32_t u) { return __uint_as_float(u << 16); }
__device__ __forceinline__ float bf_hi(uint32_t u) { return __uint_as_float(u & 0xffff0000u); }

__device__ __forceinline__ uint64_t d128(uint32_t lo) { uint64_t d; asm("mov.b64 %0, {%1, 0x40000040};" : "=l"(d) : "r"(lo)); return d; }
__device__ __forceinline__ uint64_t d64(uint32_t lo) { uint64_t d; asm("mov.b64 %0, {%1, 0x80000020};" : "=l"(d) : "r"(lo)); return d; }
template<int O,int TB,int ACC,int NN> __device__ __forceinline__ void mma_ss64(float (&d)[NN], uint64_t da, uint64_t db, int sd = 0){
  if constexpr (ACC == 1) asm volatile("wgmma.mma_async.sync.aligned.m64n64k16.f32.bf16.bf16 {%0,%1,%2,%3,%4,%5,%6,%7,%8,%9,%10,%11,%12,%13,%14,%15,%16,%17,%18,%19,%20,%21,%22,%23,%24,%25,%26,%27,%28,%29,%30,%31}, %32, %33, 1, 1, 1, 0, %34;"
   : "+f"(d[O+0]), "+f"(d[O+1]), "+f"(d[O+2]), "+f"(d[O+3]), "+f"(d[O+4]), "+f"(d[O+5]), "+f"(d[O+6]), "+f"(d[O+7]), "+f"(d[O+8]), "+f"(d[O+9]), "+f"(d[O+10]), "+f"(d[O+11]), "+f"(d[O+12]), "+f"(d[O+13]), "+f"(d[O+14]), "+f"(d[O+15]), "+f"(d[O+16]), "+f"(d[O+17]), "+f"(d[O+18]), "+f"(d[O+19]), "+f"(d[O+20]), "+f"(d[O+21]), "+f"(d[O+22]), "+f"(d[O+23]), "+f"(d[O+24]), "+f"(d[O+25]), "+f"(d[O+26]), "+f"(d[O+27]), "+f"(d[O+28]), "+f"(d[O+29]), "+f"(d[O+30]), "+f"(d[O+31])
   : "l"(da), "l"(db), "n"(TB));
  else if constexpr (ACC == 0) asm volatile("wgmma.mma_async.sync.aligned.m64n64k16.f32.bf16.bf16 {%0,%1,%2,%3,%4,%5,%6,%7,%8,%9,%10,%11,%12,%13,%14,%15,%16,%17,%18,%19,%20,%21,%22,%23,%24,%25,%26,%27,%28,%29,%30,%31}, %32, %33, 0, 1, 1, 0, %34;"
   : "=f"(d[O+0]), "=f"(d[O+1]), "=f"(d[O+2]), "=f"(d[O+3]), "=f"(d[O+4]), "=f"(d[O+5]), "=f"(d[O+6]), "=f"(d[O+7]), "=f"(d[O+8]), "=f"(d[O+9]), "=f"(d[O+10]), "=f"(d[O+11]), "=f"(d[O+12]), "=f"(d[O+13]), "=f"(d[O+14]), "=f"(d[O+15]), "=f"(d[O+16]), "=f"(d[O+17]), "=f"(d[O+18]), "=f"(d[O+19]), "=f"(d[O+20]), "=f"(d[O+21]), "=f"(d[O+22]), "=f"(d[O+23]), "=f"(d[O+24]), "=f"(d[O+25]), "=f"(d[O+26]), "=f"(d[O+27]), "=f"(d[O+28]), "=f"(d[O+29]), "=f"(d[O+30]), "=f"(d[O+31])
   : "l"(da), "l"(db), "n"(TB));
  else asm volatile("{\n.reg .pred p;\nsetp.ne.b32 p, %35, 0;\nwgmma.mma_async.sync.aligned.m64n64k16.f32.bf16.bf16 {%0,%1,%2,%3,%4,%5,%6,%7,%8,%9,%10,%11,%12,%13,%14,%15,%16,%17,%18,%19,%20,%21,%22,%23,%24,%25,%26,%27,%28,%29,%30,%31}, %32, %33, p, 1, 1, 0, %34;\n}"
   : "+f"(d[O+0]), "+f"(d[O+1]), "+f"(d[O+2]), "+f"(d[O+3]), "+f"(d[O+4]), "+f"(d[O+5]), "+f"(d[O+6]), "+f"(d[O+7]), "+f"(d[O+8]), "+f"(d[O+9]), "+f"(d[O+10]), "+f"(d[O+11]), "+f"(d[O+12]), "+f"(d[O+13]), "+f"(d[O+14]), "+f"(d[O+15]), "+f"(d[O+16]), "+f"(d[O+17]), "+f"(d[O+18]), "+f"(d[O+19]), "+f"(d[O+20]), "+f"(d[O+21]), "+f"(d[O+22]), "+f"(d[O+23]), "+f"(d[O+24]), "+f"(d[O+25]), "+f"(d[O+26]), "+f"(d[O+27]), "+f"(d[O+28]), "+f"(d[O+29]), "+f"(d[O+30]), "+f"(d[O+31])
   : "l"(da), "l"(db), "n"(TB), "r"(sd));
}
template<int O,int TB,int ACC,int NN> __device__ __forceinline__ void mma_rs64(float (&d)[NN], uint32_t a0, uint32_t a1, uint32_t a2, uint32_t a3, uint64_t db, int sd = 0){
  if constexpr (ACC == 1) asm volatile("wgmma.mma_async.sync.aligned.m64n64k16.f32.bf16.bf16 {%0,%1,%2,%3,%4,%5,%6,%7,%8,%9,%10,%11,%12,%13,%14,%15,%16,%17,%18,%19,%20,%21,%22,%23,%24,%25,%26,%27,%28,%29,%30,%31}, {%32,%33,%34,%35}, %36, 1, 1, 1, %37;"
   : "+f"(d[O+0]), "+f"(d[O+1]), "+f"(d[O+2]), "+f"(d[O+3]), "+f"(d[O+4]), "+f"(d[O+5]), "+f"(d[O+6]), "+f"(d[O+7]), "+f"(d[O+8]), "+f"(d[O+9]), "+f"(d[O+10]), "+f"(d[O+11]), "+f"(d[O+12]), "+f"(d[O+13]), "+f"(d[O+14]), "+f"(d[O+15]), "+f"(d[O+16]), "+f"(d[O+17]), "+f"(d[O+18]), "+f"(d[O+19]), "+f"(d[O+20]), "+f"(d[O+21]), "+f"(d[O+22]), "+f"(d[O+23]), "+f"(d[O+24]), "+f"(d[O+25]), "+f"(d[O+26]), "+f"(d[O+27]), "+f"(d[O+28]), "+f"(d[O+29]), "+f"(d[O+30]), "+f"(d[O+31])
   : "r"(a0), "r"(a1), "r"(a2), "r"(a3), "l"(db), "n"(TB));
  else if constexpr (ACC == 0) asm volatile("wgmma.mma_async.sync.aligned.m64n64k16.f32.bf16.bf16 {%0,%1,%2,%3,%4,%5,%6,%7,%8,%9,%10,%11,%12,%13,%14,%15,%16,%17,%18,%19,%20,%21,%22,%23,%24,%25,%26,%27,%28,%29,%30,%31}, {%32,%33,%34,%35}, %36, 0, 1, 1, %37;"
   : "=f"(d[O+0]), "=f"(d[O+1]), "=f"(d[O+2]), "=f"(d[O+3]), "=f"(d[O+4]), "=f"(d[O+5]), "=f"(d[O+6]), "=f"(d[O+7]), "=f"(d[O+8]), "=f"(d[O+9]), "=f"(d[O+10]), "=f"(d[O+11]), "=f"(d[O+12]), "=f"(d[O+13]), "=f"(d[O+14]), "=f"(d[O+15]), "=f"(d[O+16]), "=f"(d[O+17]), "=f"(d[O+18]), "=f"(d[O+19]), "=f"(d[O+20]), "=f"(d[O+21]), "=f"(d[O+22]), "=f"(d[O+23]), "=f"(d[O+24]), "=f"(d[O+25]), "=f"(d[O+26]), "=f"(d[O+27]), "=f"(d[O+28]), "=f"(d[O+29]), "=f"(d[O+30]), "=f"(d[O+31])
   : "r"(a0), "r"(a1), "r"(a2), "r"(a3), "l"(db), "n"(TB));
  else asm volatile("{\n.reg .pred p;\nsetp.ne.b32 p, %38, 0;\nwgmma.mma_async.sync.aligned.m64n64k16.f32.bf16.bf16 {%0,%1,%2,%3,%4,%5,%6,%7,%8,%9,%10,%11,%12,%13,%14,%15,%16,%17,%18,%19,%20,%21,%22,%23,%24,%25,%26,%27,%28,%29,%30,%31}, {%32,%33,%34,%35}, %36, p, 1, 1, %37;\n}"
   : "+f"(d[O+0]), "+f"(d[O+1]), "+f"(d[O+2]), "+f"(d[O+3]), "+f"(d[O+4]), "+f"(d[O+5]), "+f"(d[O+6]), "+f"(d[O+7]), "+f"(d[O+8]), "+f"(d[O+9]), "+f"(d[O+10]), "+f"(d[O+11]), "+f"(d[O+12]), "+f"(d[O+13]), "+f"(d[O+14]), "+f"(d[O+15]), "+f"(d[O+16]), "+f"(d[O+17]), "+f"(d[O+18]), "+f"(d[O+19]), "+f"(d[O+20]), "+f"(d[O+21]), "+f"(d[O+22]), "+f"(d[O+23]), "+f"(d[O+24]), "+f"(d[O+25]), "+f"(d[O+26]), "+f"(d[O+27]), "+f"(d[O+28]), "+f"(d[O+29]), "+f"(d[O+30]), "+f"(d[O+31])
   : "r"(a0), "r"(a1), "r"(a2), "r"(a3), "l"(db), "n"(TB), "r"(sd));
}
template<int O,int TB,int ACC,int NN> __device__ __forceinline__ void mma_ss128(float (&d)[NN], uint64_t da, uint64_t db, int sd = 0){
  if constexpr (ACC == 1) asm volatile("wgmma.mma_async.sync.aligned.m64n128k16.f32.bf16.bf16 {%0,%1,%2,%3,%4,%5,%6,%7,%8,%9,%10,%11,%12,%13,%14,%15,%16,%17,%18,%19,%20,%21,%22,%23,%24,%25,%26,%27,%28,%29,%30,%31,%32,%33,%34,%35,%36,%37,%38,%39,%40,%41,%42,%43,%44,%45,%46,%47,%48,%49,%50,%51,%52,%53,%54,%55,%56,%57,%58,%59,%60,%61,%62,%63}, %64, %65, 1, 1, 1, 0, %66;"
   : "+f"(d[O+0]), "+f"(d[O+1]), "+f"(d[O+2]), "+f"(d[O+3]), "+f"(d[O+4]), "+f"(d[O+5]), "+f"(d[O+6]), "+f"(d[O+7]), "+f"(d[O+8]), "+f"(d[O+9]), "+f"(d[O+10]), "+f"(d[O+11]), "+f"(d[O+12]), "+f"(d[O+13]), "+f"(d[O+14]), "+f"(d[O+15]), "+f"(d[O+16]), "+f"(d[O+17]), "+f"(d[O+18]), "+f"(d[O+19]), "+f"(d[O+20]), "+f"(d[O+21]), "+f"(d[O+22]), "+f"(d[O+23]), "+f"(d[O+24]), "+f"(d[O+25]), "+f"(d[O+26]), "+f"(d[O+27]), "+f"(d[O+28]), "+f"(d[O+29]), "+f"(d[O+30]), "+f"(d[O+31]), "+f"(d[O+32]), "+f"(d[O+33]), "+f"(d[O+34]), "+f"(d[O+35]), "+f"(d[O+36]), "+f"(d[O+37]), "+f"(d[O+38]), "+f"(d[O+39]), "+f"(d[O+40]), "+f"(d[O+41]), "+f"(d[O+42]), "+f"(d[O+43]), "+f"(d[O+44]), "+f"(d[O+45]), "+f"(d[O+46]), "+f"(d[O+47]), "+f"(d[O+48]), "+f"(d[O+49]), "+f"(d[O+50]), "+f"(d[O+51]), "+f"(d[O+52]), "+f"(d[O+53]), "+f"(d[O+54]), "+f"(d[O+55]), "+f"(d[O+56]), "+f"(d[O+57]), "+f"(d[O+58]), "+f"(d[O+59]), "+f"(d[O+60]), "+f"(d[O+61]), "+f"(d[O+62]), "+f"(d[O+63])
   : "l"(da), "l"(db), "n"(TB));
  else if constexpr (ACC == 0) asm volatile("wgmma.mma_async.sync.aligned.m64n128k16.f32.bf16.bf16 {%0,%1,%2,%3,%4,%5,%6,%7,%8,%9,%10,%11,%12,%13,%14,%15,%16,%17,%18,%19,%20,%21,%22,%23,%24,%25,%26,%27,%28,%29,%30,%31,%32,%33,%34,%35,%36,%37,%38,%39,%40,%41,%42,%43,%44,%45,%46,%47,%48,%49,%50,%51,%52,%53,%54,%55,%56,%57,%58,%59,%60,%61,%62,%63}, %64, %65, 0, 1, 1, 0, %66;"
   : "=f"(d[O+0]), "=f"(d[O+1]), "=f"(d[O+2]), "=f"(d[O+3]), "=f"(d[O+4]), "=f"(d[O+5]), "=f"(d[O+6]), "=f"(d[O+7]), "=f"(d[O+8]), "=f"(d[O+9]), "=f"(d[O+10]), "=f"(d[O+11]), "=f"(d[O+12]), "=f"(d[O+13]), "=f"(d[O+14]), "=f"(d[O+15]), "=f"(d[O+16]), "=f"(d[O+17]), "=f"(d[O+18]), "=f"(d[O+19]), "=f"(d[O+20]), "=f"(d[O+21]), "=f"(d[O+22]), "=f"(d[O+23]), "=f"(d[O+24]), "=f"(d[O+25]), "=f"(d[O+26]), "=f"(d[O+27]), "=f"(d[O+28]), "=f"(d[O+29]), "=f"(d[O+30]), "=f"(d[O+31]), "=f"(d[O+32]), "=f"(d[O+33]), "=f"(d[O+34]), "=f"(d[O+35]), "=f"(d[O+36]), "=f"(d[O+37]), "=f"(d[O+38]), "=f"(d[O+39]), "=f"(d[O+40]), "=f"(d[O+41]), "=f"(d[O+42]), "=f"(d[O+43]), "=f"(d[O+44]), "=f"(d[O+45]), "=f"(d[O+46]), "=f"(d[O+47]), "=f"(d[O+48]), "=f"(d[O+49]), "=f"(d[O+50]), "=f"(d[O+51]), "=f"(d[O+52]), "=f"(d[O+53]), "=f"(d[O+54]), "=f"(d[O+55]), "=f"(d[O+56]), "=f"(d[O+57]), "=f"(d[O+58]), "=f"(d[O+59]), "=f"(d[O+60]), "=f"(d[O+61]), "=f"(d[O+62]), "=f"(d[O+63])
   : "l"(da), "l"(db), "n"(TB));
  else asm volatile("{\n.reg .pred p;\nsetp.ne.b32 p, %67, 0;\nwgmma.mma_async.sync.aligned.m64n128k16.f32.bf16.bf16 {%0,%1,%2,%3,%4,%5,%6,%7,%8,%9,%10,%11,%12,%13,%14,%15,%16,%17,%18,%19,%20,%21,%22,%23,%24,%25,%26,%27,%28,%29,%30,%31,%32,%33,%34,%35,%36,%37,%38,%39,%40,%41,%42,%43,%44,%45,%46,%47,%48,%49,%50,%51,%52,%53,%54,%55,%56,%57,%58,%59,%60,%61,%62,%63}, %64, %65, p, 1, 1, 0, %66;\n}"
   : "+f"(d[O+0]), "+f"(d[O+1]), "+f"(d[O+2]), "+f"(d[O+3]), "+f"(d[O+4]), "+f"(d[O+5]), "+f"(d[O+6]), "+f"(d[O+7]), "+f"(d[O+8]), "+f"(d[O+9]), "+f"(d[O+10]), "+f"(d[O+11]), "+f"(d[O+12]), "+f"(d[O+13]), "+f"(d[O+14]), "+f"(d[O+15]), "+f"(d[O+16]), "+f"(d[O+17]), "+f"(d[O+18]), "+f"(d[O+19]), "+f"(d[O+20]), "+f"(d[O+21]), "+f"(d[O+22]), "+f"(d[O+23]), "+f"(d[O+24]), "+f"(d[O+25]), "+f"(d[O+26]), "+f"(d[O+27]), "+f"(d[O+28]), "+f"(d[O+29]), "+f"(d[O+30]), "+f"(d[O+31]), "+f"(d[O+32]), "+f"(d[O+33]), "+f"(d[O+34]), "+f"(d[O+35]), "+f"(d[O+36]), "+f"(d[O+37]), "+f"(d[O+38]), "+f"(d[O+39]), "+f"(d[O+40]), "+f"(d[O+41]), "+f"(d[O+42]), "+f"(d[O+43]), "+f"(d[O+44]), "+f"(d[O+45]), "+f"(d[O+46]), "+f"(d[O+47]), "+f"(d[O+48]), "+f"(d[O+49]), "+f"(d[O+50]), "+f"(d[O+51]), "+f"(d[O+52]), "+f"(d[O+53]), "+f"(d[O+54]), "+f"(d[O+55]), "+f"(d[O+56]), "+f"(d[O+57]), "+f"(d[O+58]), "+f"(d[O+59]), "+f"(d[O+60]), "+f"(d[O+61]), "+f"(d[O+62]), "+f"(d[O+63])
   : "l"(da), "l"(db), "n"(TB), "r"(sd));
}
template<int O,int TB,int ACC,int NN> __device__ __forceinline__ void mma_rs128(float (&d)[NN], uint32_t a0, uint32_t a1, uint32_t a2, uint32_t a3, uint64_t db, int sd = 0){
  if constexpr (ACC == 1) asm volatile("wgmma.mma_async.sync.aligned.m64n128k16.f32.bf16.bf16 {%0,%1,%2,%3,%4,%5,%6,%7,%8,%9,%10,%11,%12,%13,%14,%15,%16,%17,%18,%19,%20,%21,%22,%23,%24,%25,%26,%27,%28,%29,%30,%31,%32,%33,%34,%35,%36,%37,%38,%39,%40,%41,%42,%43,%44,%45,%46,%47,%48,%49,%50,%51,%52,%53,%54,%55,%56,%57,%58,%59,%60,%61,%62,%63}, {%64,%65,%66,%67}, %68, 1, 1, 1, %69;"
   : "+f"(d[O+0]), "+f"(d[O+1]), "+f"(d[O+2]), "+f"(d[O+3]), "+f"(d[O+4]), "+f"(d[O+5]), "+f"(d[O+6]), "+f"(d[O+7]), "+f"(d[O+8]), "+f"(d[O+9]), "+f"(d[O+10]), "+f"(d[O+11]), "+f"(d[O+12]), "+f"(d[O+13]), "+f"(d[O+14]), "+f"(d[O+15]), "+f"(d[O+16]), "+f"(d[O+17]), "+f"(d[O+18]), "+f"(d[O+19]), "+f"(d[O+20]), "+f"(d[O+21]), "+f"(d[O+22]), "+f"(d[O+23]), "+f"(d[O+24]), "+f"(d[O+25]), "+f"(d[O+26]), "+f"(d[O+27]), "+f"(d[O+28]), "+f"(d[O+29]), "+f"(d[O+30]), "+f"(d[O+31]), "+f"(d[O+32]), "+f"(d[O+33]), "+f"(d[O+34]), "+f"(d[O+35]), "+f"(d[O+36]), "+f"(d[O+37]), "+f"(d[O+38]), "+f"(d[O+39]), "+f"(d[O+40]), "+f"(d[O+41]), "+f"(d[O+42]), "+f"(d[O+43]), "+f"(d[O+44]), "+f"(d[O+45]), "+f"(d[O+46]), "+f"(d[O+47]), "+f"(d[O+48]), "+f"(d[O+49]), "+f"(d[O+50]), "+f"(d[O+51]), "+f"(d[O+52]), "+f"(d[O+53]), "+f"(d[O+54]), "+f"(d[O+55]), "+f"(d[O+56]), "+f"(d[O+57]), "+f"(d[O+58]), "+f"(d[O+59]), "+f"(d[O+60]), "+f"(d[O+61]), "+f"(d[O+62]), "+f"(d[O+63])
   : "r"(a0), "r"(a1), "r"(a2), "r"(a3), "l"(db), "n"(TB));
  else if constexpr (ACC == 0) asm volatile("wgmma.mma_async.sync.aligned.m64n128k16.f32.bf16.bf16 {%0,%1,%2,%3,%4,%5,%6,%7,%8,%9,%10,%11,%12,%13,%14,%15,%16,%17,%18,%19,%20,%21,%22,%23,%24,%25,%26,%27,%28,%29,%30,%31,%32,%33,%34,%35,%36,%37,%38,%39,%40,%41,%42,%43,%44,%45,%46,%47,%48,%49,%50,%51,%52,%53,%54,%55,%56,%57,%58,%59,%60,%61,%62,%63}, {%64,%65,%66,%67}, %68, 0, 1, 1, %69;"
   : "=f"(d[O+0]), "=f"(d[O+1]), "=f"(d[O+2]), "=f"(d[O+3]), "=f"(d[O+4]), "=f"(d[O+5]), "=f"(d[O+6]), "=f"(d[O+7]), "=f"(d[O+8]), "=f"(d[O+9]), "=f"(d[O+10]), "=f"(d[O+11]), "=f"(d[O+12]), "=f"(d[O+13]), "=f"(d[O+14]), "=f"(d[O+15]), "=f"(d[O+16]), "=f"(d[O+17]), "=f"(d[O+18]), "=f"(d[O+19]), "=f"(d[O+20]), "=f"(d[O+21]), "=f"(d[O+22]), "=f"(d[O+23]), "=f"(d[O+24]), "=f"(d[O+25]), "=f"(d[O+26]), "=f"(d[O+27]), "=f"(d[O+28]), "=f"(d[O+29]), "=f"(d[O+30]), "=f"(d[O+31]), "=f"(d[O+32]), "=f"(d[O+33]), "=f"(d[O+34]), "=f"(d[O+35]), "=f"(d[O+36]), "=f"(d[O+37]), "=f"(d[O+38]), "=f"(d[O+39]), "=f"(d[O+40]), "=f"(d[O+41]), "=f"(d[O+42]), "=f"(d[O+43]), "=f"(d[O+44]), "=f"(d[O+45]), "=f"(d[O+46]), "=f"(d[O+47]), "=f"(d[O+48]), "=f"(d[O+49]), "=f"(d[O+50]), "=f"(d[O+51]), "=f"(d[O+52]), "=f"(d[O+53]), "=f"(d[O+54]), "=f"(d[O+55]), "=f"(d[O+56]), "=f"(d[O+57]), "=f"(d[O+58]), "=f"(d[O+59]), "=f"(d[O+60]), "=f"(d[O+61]), "=f"(d[O+62]), "=f"(d[O+63])
   : "r"(a0), "r"(a1), "r"(a2), "r"(a3), "l"(db), "n"(TB));
  else asm volatile("{\n.reg .pred p;\nsetp.ne.b32 p, %70, 0;\nwgmma.mma_async.sync.aligned.m64n128k16.f32.bf16.bf16 {%0,%1,%2,%3,%4,%5,%6,%7,%8,%9,%10,%11,%12,%13,%14,%15,%16,%17,%18,%19,%20,%21,%22,%23,%24,%25,%26,%27,%28,%29,%30,%31,%32,%33,%34,%35,%36,%37,%38,%39,%40,%41,%42,%43,%44,%45,%46,%47,%48,%49,%50,%51,%52,%53,%54,%55,%56,%57,%58,%59,%60,%61,%62,%63}, {%64,%65,%66,%67}, %68, p, 1, 1, %69;\n}"
   : "+f"(d[O+0]), "+f"(d[O+1]), "+f"(d[O+2]), "+f"(d[O+3]), "+f"(d[O+4]), "+f"(d[O+5]), "+f"(d[O+6]), "+f"(d[O+7]), "+f"(d[O+8]), "+f"(d[O+9]), "+f"(d[O+10]), "+f"(d[O+11]), "+f"(d[O+12]), "+f"(d[O+13]), "+f"(d[O+14]), "+f"(d[O+15]), "+f"(d[O+16]), "+f"(d[O+17]), "+f"(d[O+18]), "+f"(d[O+19]), "+f"(d[O+20]), "+f"(d[O+21]), "+f"(d[O+22]), "+f"(d[O+23]), "+f"(d[O+24]), "+f"(d[O+25]), "+f"(d[O+26]), "+f"(d[O+27]), "+f"(d[O+28]), "+f"(d[O+29]), "+f"(d[O+30]), "+f"(d[O+31]), "+f"(d[O+32]), "+f"(d[O+33]), "+f"(d[O+34]), "+f"(d[O+35]), "+f"(d[O+36]), "+f"(d[O+37]), "+f"(d[O+38]), "+f"(d[O+39]), "+f"(d[O+40]), "+f"(d[O+41]), "+f"(d[O+42]), "+f"(d[O+43]), "+f"(d[O+44]), "+f"(d[O+45]), "+f"(d[O+46]), "+f"(d[O+47]), "+f"(d[O+48]), "+f"(d[O+49]), "+f"(d[O+50]), "+f"(d[O+51]), "+f"(d[O+52]), "+f"(d[O+53]), "+f"(d[O+54]), "+f"(d[O+55]), "+f"(d[O+56]), "+f"(d[O+57]), "+f"(d[O+58]), "+f"(d[O+59]), "+f"(d[O+60]), "+f"(d[O+61]), "+f"(d[O+62]), "+f"(d[O+63])
   : "r"(a0), "r"(a1), "r"(a2), "r"(a3), "l"(db), "n"(TB), "r"(sd));
}

#define NEARLY 2
#define XAHEAD 3
#define WAFTER 3
#define WPACE 50
#define GATE_AT 0
#define TPACE 40
#define PFMODE 0
#define MAPMODE 0
template <int V> struct IC { static constexpr int value = V; };
struct Maps { CUtensorMap ft, g32, x, u32, g64, u64, e, d192, d32, fg; };

constexpr int NCTA = 132;
constexpr int U = 16384;
constexpr int TB = 36864;
constexpr int NR = 5;
constexpr int OFF_RING = 8 * U, OFF_Z = 9 * U, OFF_T = 13 * U;
constexpr int OFF_BAR = 14 * U;
constexpr int SMEM_BYTES = OFF_BAR + 512;
constexpr int B_FX = 0, B_FA = 8, B_FT = 13, B_Z = 17, B_W = 21, B_HX = 22, B_HT = 23, B_HP = 24;
constexpr int B_EA = 27, B_ET = 32, B_RDY = 36;
constexpr int B_T = 37, NBAR = 38;
__host__ __device__ constexpr int rslot(int n) { return (n + 2) % NR; }
__host__ __device__ constexpr int rpar(int n) { return (n / NR) & 1; }

__global__ void __cluster_dims__(2, 1, 1) __launch_bounds__(512, 1)
fused_kernel(const __grid_constant__ Maps maps, const __nv_bfloat16* __restrict__ x, const __nv_bfloat16* __restrict__ w_r,
             const __nv_bfloat16* __restrict__ w_i, const __nv_bfloat16* __restrict__ gate_w, const __nv_bfloat16* __restrict__ Wg,
             const __nv_bfloat16* __restrict__ Wu, __nv_bfloat16* __restrict__ out) {
  extern __shared__ __align__(1024) uint8_t smem[];
  const uint32_t sb = smem_u32(smem);
  const uint32_t bars = sb + OFF_BAR;
  const int tid = threadIdx.x, lane = tid & 31;
  const int warp = __shfl_sync(0xffffffffu, tid >> 5, 0);
  const bool helper = blockIdx.x >= 128;
  const int cl = (blockIdx.x >> 1) & 63, rank = blockIdx.x & 1;
  const int q4 = cl & 3, rb = cl >> 2;
  const int j = 2 * q4 + rank;
  const int f_full = 448 * q4 + (rank ? 256 : 0);
  const int f_half = 448 * q4 + (rank ? 224 : 192);
  const int kg = 2 * j + (rb >> 3), tn = rb & 7;

  if (tid == 64) { PROF_EV(0); PROF_CK(40); }
  auto ring_part = [&](int p, int n, int slot) {
    const uint32_t fb = bars + 8 * (B_FA + slot), dst = sb + OFF_RING + slot * U;
    const bool table = n == 9 || n == 10 || n >= 34;
    const int q = n == 8 ? 0 : n - 10;
    if (p == 0) {
      mbar_expect_tx(fb, U);
      if (n < 8) tma2d(dst, &maps.ft, fb, 64 * n, 64 * j);
      else if (table) tma4d(dst, &maps.e, fb, 0, 0, 0, 2 * rb + (n >= 34 ? n - 34 : n - 9));
      else tma2d(dst, &maps.g64, fb, f_full + 64 * (q >> 3), 64 * (q & 7));
    } else if (p == 1) {
      if (n < 8) { tma2d(dst + 8192, &maps.g32, fb, f_half, 64 * n); tma2d(dst + 12288, &maps.u32, fb, f_half, 64 * n); }
      else if (!table) tma2d(dst + 8192, &maps.u64, fb, f_full + 64 * (q >> 3), 64 * (q & 7));
    }
  };
  auto x_load = [&](int q) {
    mbar_expect_tx(bars + 8 * (B_FX + q), U);
    tma3d(sb + q * U, &maps.x, bars + 8 * (B_FX + q), 64 * q, 0, 2 * rb);
  };
  if (warp < 8) {
    if (!helper) {
      const int r8 = tid >> 3, c8 = tid & 7, r4 = tid >> 2, c4 = tid & 3;
      const uint32_t sw8 = r8 * 128 + ((c8 ^ (r8 & 7)) << 4), sw4 = r4 * 64 + ((c4 ^ ((r4 >> 1) & 3)) << 4);
      const __nv_bfloat16* px = x + (size_t)(2 * rb + 32 * r8) * 512 + 8 * c8;
      const uint16_t* pf = g_FT.v + (64 * j + r8) * 512 + 8 * c8;
      const size_t om = (size_t)r4 * 1792 + f_half + 8 * c4;
#pragma unroll
      for (int kb = 0; kb < NEARLY; kb++) {
        const uint32_t dst = sb + OFF_RING + rslot(kb) * U;
#pragma unroll
        for (int i = 0; i < 4; i++) cp16(sb + kb * U + i * 4096 + sw8, px + (i & 1) * 32 * 32 * 512 + (i >> 1) * 512 + 64 * kb);
        cp16(dst + sw8, pf + 64 * kb); cp16(dst + 4096 + sw8, pf + 32 * 512 + 64 * kb);
        cp16(dst + 8192 + sw4, Wg + om + kb * 64 * 1792); cp16(dst + 12288 + sw4, Wu + om + kb * 64 * 1792);
        asm volatile("cp.async.commit_group;" ::: "memory");
      }
    }
  } else if (warp >= 12 && lane == 0) {
    asm volatile("prefetch.tensormap [%0];" ::"l"((const char*)&maps + (warp - 12) * 128) : "memory");
    if (warp == 15) {
#pragma unroll
      for (int i = B_FT; i < NBAR; i++) mbar_init(bars + 8 * i, i < B_EA ? 1 : i < B_T ? 2 : 4);
#pragma unroll
      for (int i = 0; i < 4; i++) mbar_expect_tx(bars + 8 * (B_Z + i), U);
      asm volatile("fence.mbarrier_init.release.cluster;" ::: "memory");
    } else if (warp == 14) {
#pragma unroll
      for (int i = 0; i < B_FT; i++) mbar_init(bars + 8 * i, 1);
#pragma unroll
      for (int i = 0; i < NEARLY; i++) mbar_arrive(bars + 8 * (B_FA + rslot(i)));
    } else if (warp == 13) {
#pragma unroll
      for (int i = 4; i < 10; i++) asm volatile("prefetch.tensormap [%0];" ::"l"((const char*)&maps + i * 128) : "memory");
    }
    asm volatile("fence.proxy.async.shared::cta;" ::: "memory");
  }
  if (warp >= 8) {
    __syncwarp();
    asm volatile("bar.arrive 0, 512;" ::: "memory");
    asm volatile("bar.sync 3, 256;" ::: "memory");
  }
  asm volatile("barrier.cluster.arrive.relaxed.aligned;" ::: "memory");
  if (tid == 64) PROF_EV(38);

  if (warp >= 12) {
    asm volatile("setmaxnreg.dec.sync.aligned.u32 24;");
    if (lane == 0 && !helper) {
      if (warp < 14) {
        int slot = rslot(NEARLY), par = 1;
#pragma unroll 1
        for (int n = NEARLY; n < 36; n++) {
          mbar_wait(bars + 8 * (B_EA + slot), par);
          ring_part(warp - 12, n, slot);
          if (++slot == NR) slot = 0;
          if (slot == rslot(0)) par ^= 1;
        }
      } else if (warp == 15) {
        const unsigned ep1 = ld_x1(&g_epoch[blockIdx.x * 8]) + 1;
        hint_wait(&g_cntX[32 * j], ep1 * 128u); mbar_arrive(bars + 8 * B_HX);
        hint_wait(&g_cntT[32 * j], ep1 * (j == 0 ? 80u : 64u)); mbar_arrive(bars + 8 * B_HT);
#pragma unroll 1
        for (int i = 0; i < 3; i++) { hint_wait(&g_cntP[32 * (rb * 8 + j) + i], ep1 * 8u); mbar_arrive(bars + 8 * (B_HP + i)); }
      } else {
#pragma unroll 1
        for (int q = NEARLY; q < 8; q++) { if (q >= NEARLY + XAHEAD) mbar_wait(bars + 8 * (B_FX + q - XAHEAD), 0); x_load(q); }
        PROF_EV(31);
#pragma unroll 1
        for (int t = 0; t < 8; t++) {
          const int i = t < 3 ? t + 1 : t < 6 ? t - 2 : 0;
          const int col = 64 * (2 * ((q4 + i) & 3) + ((t < 3 || t == 6) ? 1 - rank : rank));
          const uint32_t fb = bars + 8 * (B_FT + (t & 3)), dst = sb + (t & 3) * TB;
          mbar_wait(bars + 8 * (B_ET + (t & 3)), t >> 2);
          mbar_expect_tx(fb, TB);
          tma2d(dst, &maps.d192, fb, col, f_full);
          tma2d(dst + 24576, &maps.d32, fb, col, f_half);
          tma4d(dst + 28672, &maps.fg, fb, col, 0, 0, 4 * j);
        }
      }
    }
  } else if (warp >= 8) {
    asm volatile("setmaxnreg.dec.sync.aligned.u32 104;");
    const int t = tid - 256, w = warp - 8;
    const uint32_t ep = ld_x1(&g_epoch[blockIdx.x * 8]);
    const uint32_t tag = (ep + 1) & 1;
    auto gate_rows = [&] {
      uint4 xv[8], gv[2];
#pragma unroll
      for (int i = 0; i < 4; i++) {
        const int r = 16 * j + 4 * w + i;
        const uint4* p = (const uint4*)(x + (size_t)(2 * rb + (r >> 6) + 32 * (r & 63)) * 512) + lane;
        xv[2 * i] = __ldg(p); xv[2 * i + 1] = __ldg(p + 32);
      }
      gv[0] = __ldg((const uint4*)gate_w + lane); gv[1] = __ldg((const uint4*)gate_w + lane + 32);
      {
        float z[4];
#pragma unroll
        for (int i = 0; i < 4; i++) {
          float a = 0.f;
#pragma unroll
          for (int hh = 0; hh < 2; hh++) {
            const uint4 u = xv[2 * i + hh], v = gv[hh];
            a = fmaf(bf_lo(u.x), bf_lo(v.x), a); a = fmaf(bf_hi(u.x), bf_hi(v.x), a);
            a = fmaf(bf_lo(u.y), bf_lo(v.y), a); a = fmaf(bf_hi(u.y), bf_hi(v.y), a);
            a = fmaf(bf_lo(u.z), bf_lo(v.z), a); a = fmaf(bf_hi(u.z), bf_hi(v.z), a);
            a = fmaf(bf_lo(u.w), bf_lo(v.w), a); a = fmaf(bf_hi(u.w), bf_hi(v.w), a);
          }
#pragma unroll
          for (int o = 16; o; o >>= 1) a += __shfl_xor_sync(0xffffffffu, a, o);
          z[i] = a;
        }
        if (lane < 4) {
          const float zz = lane == 0 ? z[0] : lane == 1 ? z[1] : lane == 2 ? z[2] : z[3];
          asm volatile("st.relaxed.gpu.global.f32 [%0], %1;" ::"l"(g_gate + rb * 128 + 16 * j + 4 * w + lane), "f"(tagf(1.0f / (1.0f + __expf(-zz)), tag)) : "memory");
        }
        if (t == 0) PROF_EV(18);
      }
      if (w == 0) {
        const int c = lane >> 4, jj = 16 * blockIdx.x + (lane & 15), jm = (2048 - jj) & 2047;
        const unsigned short* pr = (const unsigned short*)w_r + 256 * c;
        const unsigned short* pi = (const unsigned short*)w_i + 256 * c;
        const float wr = 0.25f * (bf_lo(__ldg(pr + jj * 257)) + bf_lo(__ldg(pr + jm * 257)));
        const float wi = 0.25f * (bf_lo(__ldg(pi + jj * 257)) - bf_lo(__ldg(pi + jm * 257)));
        st_u2(g_Wh + c * 2048 + jj, c ? pack_bf16(-wi, wr) : pack_bf16(wr, wi), tag);
        __syncwarp();
        if (lane == 0) hint_add(&g_cntW[0]);
      }
    };
    {
      const int g = lane >> 2, q = lane & 3;
      uint32_t wf[32];
      if (t == 0) { mbar_expect_tx(bars + 8 * B_W, 8192); bulk_load(sb + OFF_T, g_DT.v, 8192, bars + 8 * B_W); }
      if (!helper) {
        mbar_wait(bars + 8 * (B_FX + WAFTER), 0);
        if (t == 0) PROF_EV(32);
        gate_rows();
        const int o = (8 * tn + 2 * w + 64 * q) * 257 + 16 * kg + g;
        const unsigned short* pr = (const unsigned short*)w_r + o;
        const unsigned short* pi = (const unsigned short*)w_i + o;
#pragma unroll
        for (int i = 0; i < 32; i++) {
          const int d = (i >> 4) * 8 + (i & 1) * 257 + ((i >> 1) & 7) * 256 * 257;
          wf[i] = (uint32_t)__ldg(pr + d) | ((uint32_t)__ldg(pi + d) << 16);
        }
      } else {
        hint_wait(&g_cntW[0], (ep + 1) * 128u);
        const uint32_t t0 = (uint32_t)clock();
#pragma unroll 1
        for (;;) {
          uint32_t bad = 0;
#pragma unroll
          for (int i = 0; i < 16; i++) {
            const uint4 v = ld_x4(g_Wh + (i >> 3) * 2048 + 16 * w + 2 * g + 64 * q + (i & 7) * 256);
            wf[2 * i] = v.x; wf[2 * i + 1] = v.z; bad |= (v.y ^ tag) | (v.w ^ tag);
          }
          if (!__any_sync(0xffffffffu, bad & 1)) break;
          spin_guard(t0);
        }
      }
#pragma unroll
      for (int i = 0; i < 4; i++) *(uint4*)(smem + OFF_T + 8192 + (i * 128 + t) * 16) = make_uint4(wf[16 + 4 * i], wf[17 + 4 * i], wf[18 + 4 * i], wf[19 + 4 * i]);
#pragma unroll
      for (int i = 0; i < 16; i++) asm volatile("" : "+r"(wf[i])::"memory");
      if (t == 0) PROF_EV(11);
      if (helper) hint_wait(&g_cntX[0], (ep + 1) * 128u); else mbar_wait(bars + 8 * B_HX, 0);
      if (t == 0) PROF_EV(22);
      uint32_t xf[32];
      {
        const float2* src = (const float2*)g_X1p + (size_t)(helper ? 128 : kg * 8 + tn) * 2048 + q * 128 + w * 8 + g;
        const uint32_t t0 = (uint32_t)clock();
#pragma unroll 1
        for (;;) {
          uint32_t bad = 0;
#pragma unroll
          for (int i = 0; i < 16; i++) {
            const float2 v = ld_x2(src + (i >> 3) * 32 + ((i >> 1) & 3) * 512 + (i & 1) * 64);
            xf[2 * i] = __float_as_uint(v.x); xf[2 * i + 1] = __float_as_uint(v.y);
          }
#pragma unroll
          for (int i = 0; i < 16; i++) bad |= xf[2 * i] ^ tag;
          if (!__any_sync(0xffffffffu, bad & 1)) break;
          spin_guard(t0);
        }
#pragma unroll
        for (int i = 0; i < 16; i++) xf[2 * i] &= ~1u;
      }
      if (t == 0) PROF_EV(12);
      mbar_wait(bars + 8 * B_W, 0);
      const uint32_t dd = ((sb + OFF_T) & 0x3FFFF) >> 4;
      const uint64_t dF = d128(dd | (512u << 16)), dI = d128(dd | (1u << 16));
      uint2* dst = helper ? g_T + q * 2048 + (16 * w + 2 * g) * 16 : g_T + (size_t)j * 32768 + q * 2048 + (kg & 1) * 1024 + (8 * tn + 2 * w) * 16 + g;
      float az[32];
      const int zero = blockIdx.x >> 16;
      uint32_t pf[32];
#pragma unroll
      for (int mt = 0; mt < 2; mt++) {
        wg_fence();
        if (mt == 0) mma_rs64<0, 1, 0>(az, xf[0], xf[1], xf[2], xf[3], dF);
        else mma_rs64<0, 1, 2>(az, xf[16], xf[17], xf[18], xf[19], dF, zero);
#pragma unroll
        for (int k = 1; k < 4; k++) mma_rs64<0, 1, 1>(az, xf[16 * mt + 4 * k], xf[16 * mt + 4 * k + 1], xf[16 * mt + 4 * k + 2], xf[16 * mt + 4 * k + 3], dF + k * 128);
        wg_commit();
        if (mt == 1) {
#pragma unroll
          for (int i = 0; i < 4; i++) {
            const uint4 v = *(const uint4*)(smem + OFF_T + 8192 + (i * 128 + t) * 16);
            wf[4 * i] = v.x; wf[4 * i + 1] = v.y; wf[4 * i + 2] = v.z; wf[4 * i + 3] = v.w;
          }
        }
        wg_wait<0>();
        fence_regs<0, 32>(az);
#pragma unroll
        for (int i = 0; i < 16; i++) {
          const float wr = bf_lo(wf[i]), wi = bf_hi(wf[i]);
          pf[16 * mt + i] = pack_pin(fmaf(az[2 * i], wr, -az[2 * i + 1] * wi), fmaf(az[2 * i], wi, az[2 * i + 1] * wr));
        }
      }
#pragma unroll
      for (int mt = 0; mt < 2; mt++) {
        wg_fence();
        if (mt == 0) mma_rs64<0, 0, 2>(az, pf[0], pf[1], pf[2], pf[3], dI, zero);
        else mma_rs64<0, 0, 2>(az, pf[16], pf[17], pf[18], pf[19], dI, helper);
#pragma unroll
        for (int k = 1; k < 4; k++) mma_rs64<0, 0, 1>(az, pf[16 * mt + 4 * k], pf[16 * mt + 4 * k + 1], pf[16 * mt + 4 * k + 2], pf[16 * mt + 4 * k + 3], dI + k * 2);
        wg_commit();
        wg_wait<0>();
        fence_regs<0, 32>(az);
        if (mt == 0 && t == 0) PROF_EV(16);
        const bool skip = helper ? mt == 0 : (kg == 0 && mt == 0 && g == 0);
#pragma unroll
        for (int i = 0; i < 8; i++) {
          const int m = i >> 1, hi = i & 1;
          if (!skip && (!helper || m == (int)blockIdx.x - 128))
            st_u2(dst + m * 8192 + hi * 16 + (helper ? 0 : mt * 8), (pack_bf16(az[8 * m + 2 * hi], az[8 * m + 2 * hi + 1]) & ~1u) | tag,
                  pack_bf16(az[8 * m + 4 + 2 * hi], az[8 * m + 5 + 2 * hi]));
        }
      }
      __syncwarp();
      if (lane == 0) hint_add(&g_cntT[helper ? 0 : 32 * j]);
      if (t == 0) PROF_EV(17);
      if (helper) {
        if (t == 0) g_epoch[blockIdx.x * 8] = ep + 1;
      } else {
        const uint4* src = (const uint4*)(g_T + (size_t)(j * 16 + rb) * 2048) + t;
        uint4 tv[8];
        mbar_wait(bars + 8 * B_HT, 0);
        if (t == 0) PROF_EV(23);
        const uint32_t t0 = (uint32_t)clock();
#pragma unroll 1
        for (;;) {
          uint32_t bad = 0;
#pragma unroll
          for (int a = 0; a < 8; a++) tv[a] = ld_x4(src + a * 128);
#pragma unroll
          for (int a = 0; a < 8; a++) bad |= (tv[a].x ^ tag) | (tv[a].z ^ tag);
          if (!__any_sync(0xffffffffu, bad & 1)) break;
          spin_guard(t0);
        }
        const int r = t >> 3, c = t & 7;
#pragma unroll
        for (int a = 0; a < 8; a++) {
          const uint32_t dst2 = sb + OFF_T + (16 * (a & 3) + r) * 128 + ((((a >> 2) * 4 + (c >> 1)) ^ (r & 7)) << 4) + (c & 1) * 8;
          asm volatile("st.shared.v2.u32 [%0], {%1,%2};" ::"r"(dst2), "r"(tv[a].x & ~1u), "r"(tv[a].z & ~1u) : "memory");
          asm volatile("st.shared.v2.u32 [%0], {%1,%2};" ::"r"(dst2 + 8192), "r"(tv[a].y), "r"(tv[a].w) : "memory");
        }
        asm volatile("fence.proxy.async.shared::cta;" ::: "memory");
        __syncwarp();
        if (lane == 0) mbar_arrive(bars + 8 * B_T);
        if (t == 0) PROF_EV(13);
      }
    }
  } else {
    asm volatile("setmaxnreg.inc.sync.aligned.u32 192;");
    if (!helper) {
      const int wg = warp >> 2, w = warp & 3, g = lane >> 2, q = lane & 3;
      const bool elect = (tid & 127) == 0;
      const uint32_t ep = ld_x1(&g_epoch[blockIdx.x * 8]);
      float c1[64], cA[64], c2[64], ci[64], ct[64];
      const int zero = blockIdx.x >> 16;
      uint32_t h[56], yf[16];
      const uint32_t d0 = (sb & 0x3FFFF) >> 4;
      const uint32_t dK = d0 | (1u << 16), dN = d0 | (512u << 16), dM = d0 | (256u << 16);
      const uint32_t dX = dK + wg * 512;
      constexpr uint32_t RING = OFF_RING >> 4;
      auto waitA = [&](int n) { mbar_wait(bars + 8 * (B_FA + rslot(n)), rpar(n)); };
      auto freeA = [&](int n) { if (elect) mbar_arrive(bars + 8 * (B_EA + rslot(n))); };
      auto nop = [](int) {};

#pragma unroll
      for (int kb = 0; kb < 8; kb++) {
        if (kb < NEARLY) {
          if (NEARLY - 1 - kb == 3) asm volatile("cp.async.wait_group 3;" ::: "memory");
          else if (NEARLY - 1 - kb == 2) asm volatile("cp.async.wait_group 2;" ::: "memory");
          else if (NEARLY - 1 - kb == 1) asm volatile("cp.async.wait_group 1;" ::: "memory");
          else asm volatile("cp.async.wait_group 0;" ::: "memory");
          asm volatile("fence.proxy.async.shared::cta;" ::: "memory");
          if (kb == 0) asm volatile("bar.sync 0, 512;" ::: "memory");
          else asm volatile("bar.sync 2, 256;" ::: "memory");
        } else {
          mbar_wait(bars + 8 * (B_FX + kb), 0); waitA(kb);
        }
        wg_fence();
        const uint64_t dx = d128(dX + kb * 1024), df = d128(dK + RING + rslot(kb) * 1024), dm = d64(dM + RING + 512 + rslot(kb) * 1024);
        if (kb == 0) { mma_ss64<0, 0, 0>(c1, df, dx); mma_ss64<32, 1, 0>(c1, dx, dm); }
        else { mma_ss64<0, 0, 1>(c1, df, dx); mma_ss64<32, 1, 1>(c1, dx, dm); wg_commit(); wg_wait<1>(); freeA(kb - 1); }
#pragma unroll
        for (int k = 1; k < 4; k++) {
          mma_ss64<0, 0, 1>(c1, df + k * 2, dx + k * 2);
          mma_ss64<32, 1, 1>(c1, dx + k * 2, dm + k * 64);
        }
        wg_commit();
        if (kb == 0 && tid == 0) PROF_EV(1);
      }
      auto ffn_step = [&](auto first, float (&acc)[64], int n, int kb, auto done, auto work) {
        waitA(n);
        wg_fence();
        const uint64_t dx = d128(dX + kb * 1024), db = d128(dN + RING + rslot(n) * 1024);
        mma_ss128<0, 1, decltype(first)::value>(acc, dx, db, zero);
        wg_commit();
        wg_wait<1>();
        done();
#pragma unroll
        for (int k = 1; k < 4; k++) { mma_ss128<0, 1, 1>(acc, dx + k * 2, db + k * 128); work(k - 1); }
        wg_commit();
        work(3);
      };
      const uint32_t tag = (ep + 1) & 1;
      float hm[16];
      ffn_step(IC<0>(), c2, 8, 0, [&] { freeA(7); fence_regs<0, 64>(c1); }, [&](int i) {
#pragma unroll
        for (int e = 4 * i; e < 4 * i + 4; e++) { yf[e] = pack_pin(c1[2 * e], c1[2 * e + 1]); hm[e] = fmaxf(c1[32 + e], 0.f) * c1[48 + e]; }
      });
      fence_regs<0, 16>(hm);
      if (tid == 0) PROF_EV(2);
      {
        waitA(9); waitA(10);
        const uint64_t de = d128(dN + RING + (wg ? rslot(10) : rslot(9)) * 1024);
        wg_fence();
        mma_rs128<0, 1, 0>(cA, yf[0], yf[1], yf[2], yf[3], de);
        wg_commit();
        wg_wait<1>();
        freeA(8);
#pragma unroll
        for (int k = 1; k < 4; k++) mma_rs128<0, 1, 1>(cA, yf[4 * k], yf[4 * k + 1], yf[4 * k + 2], yf[4 * k + 3], de + k * 128);
        wg_commit();
      }
      {
        const int s0 = 2 * rb + wg;
        uint2* dst = g_X1p + ((size_t)((2 * j + (w >> 1)) * 8) * 32 + s0) * 64 + (w & 1) * 32 + q * 8 + g;
        auto x1_store = [&](int n) {
          st_u2(dst + n * 2048, (pack_bf16(cA[4 * n] - cA[34 + 4 * n], cA[32 + 4 * n] + cA[4 * n + 2]) & ~1u) | tag,
                pack_bf16(cA[4 * n + 1] - cA[35 + 4 * n], cA[33 + 4 * n] + cA[4 * n + 3]));
        };
        ffn_step(IC<1>(), c2, 11, 1, [&] { freeA(9); freeA(10); fence_regs<0, 64>(cA); }, [&](int i) { x1_store(i); });
        if (tid == 0) PROF_EV(19);
        ffn_step(IC<1>(), c2, 12, 2, [&] { freeA(11); }, [&](int i) { x1_store(4 + i); });
        if (j == 0 && w == 0 && g == 0) {
#pragma unroll
          for (int n = 0; n < 8; n++) {
            st_u2(g_X1p + 128 * 2048 + s0 * 64 + 4 * n + q, (pack_bf16(cA[4 * n], cA[32 + 4 * n]) & ~1u) | tag, pack_bf16(cA[4 * n + 1], cA[33 + 4 * n]));
            st_u2(g_X1p + 128 * 2048 + s0 * 64 + 32 + 4 * n + q, (pack_bf16(cA[4 * n + 2], cA[34 + 4 * n]) & ~1u) | tag, pack_bf16(cA[4 * n + 3], cA[35 + 4 * n]));
          }
        }
        __syncwarp();
        if (lane == 0) hint_add(&g_cntX[32 * j]);
        if (tid == 0) PROF_EV(3);
      }
      const float* gp = g_gate + rb * 128 + wg * 64 + w * 16 + g;
      uint32_t gb0 = ld_x1(gp), gb1 = ld_x1(gp + 8);
#pragma unroll
      for (int kb = 3; kb < 7; kb++) ffn_step(IC<1>(), c2, 10 + kb, kb, [&] { freeA(9 + kb); }, nop);
      {
        const uint32_t t0 = (uint32_t)clock();
        while (__any_sync(0xffffffffu, ((gb0 ^ tag) | (gb1 ^ tag)) & 1)) { gb0 = ld_x1(gp); gb1 = ld_x1(gp + 8); spin_guard(t0); }
      }
      const float g0 = __uint_as_float(gb0 & ~1u), g1 = __uint_as_float(gb1 & ~1u);
      const float o0 = 1.0f - g0, o1 = 1.0f - g1;
      uint32_t hp[8];
      ffn_step(IC<1>(), c2, 17, 7, [&] { freeA(16); }, [&](int i) {
        hp[2 * i] = pack_pin(hm[4 * i] * o0, hm[4 * i + 1] * o0); hp[2 * i + 1] = pack_pin(hm[4 * i + 2] * o1, hm[4 * i + 3] * o1);
      });
      auto glu = [&](float (&acc)[64], int ho, int i0, int i1) {
#pragma unroll
        for (int i = i0; i < i1; i++) {
          const float o = (i & 1) ? o1 : o0;
          h[ho + i] = pack_pin(fmaxf(acc[2 * i], 0.f) * acc[32 + 2 * i] * o, fmaxf(acc[2 * i + 1], 0.f) * acc[33 + 2 * i] * o);
        }
      };
      ffn_step(IC<2>(), cA, 18, 0, [&] { freeA(17); fence_regs<0, 64>(c2); }, [&](int i) { glu(c2, 0, 2 * i, 2 * i + 2); });
      if (tid == 0) PROF_EV(4);
      ffn_step(IC<1>(), cA, 19, 1, [&] { freeA(18); }, [&](int i) { glu(c2, 0, 8 + 2 * i, 10 + 2 * i); });
#pragma unroll
      for (int kb = 2; kb < 8; kb++) ffn_step(IC<1>(), cA, 18 + kb, kb, [&] { freeA(17 + kb); }, nop);
      ffn_step(IC<2>(), c2, 26, 0, [&] { freeA(25); fence_regs<0, 64>(cA); }, [&](int i) { glu(cA, 16, 2 * i, 2 * i + 2); });
      if (tid == 0) PROF_EV(5);
      ffn_step(IC<1>(), c2, 27, 1, [&] { freeA(26); }, [&](int i) { glu(cA, 16, 8 + 2 * i, 10 + 2 * i); });
#pragma unroll
      for (int kb = 2; kb < 8; kb++)
        ffn_step(IC<1>(), c2, 26 + kb, kb, [&] {
          if (kb < 6) freeA(25 + kb);
          if (kb >= 3 && (kb & 1) && elect) mbar_arrive(bars + 8 * (B_ET + ((kb - 3) >> 1)));
        }, nop);
      wg_wait<0>();
      if (elect) mbar_arrive(bars + 8 * (B_ET + 3));
      fence_regs<0, 64>(c2);
      glu(c2, 32, 0, 16);
#pragma unroll
      for (int i = 0; i < 8; i++) h[48 + i] = hp[i] ^ zero;
      if (wg) waitA(35); else waitA(34);
      if (tid == 0) PROF_EV(6);
      mbar_wait(bars + 8 * B_T, 0);
      if (tid == 0) PROF_EV(7);
      wg_fence();
      {
        const uint64_t dt = d128(dN + (OFF_T >> 4) + wg * 512), de = d128(dK + RING + (wg ? rslot(35) : rslot(34)) * 1024);
        mma_ss64<0, 1, 0>(ci, de, dt);
        mma_ss64<32, 1, 0>(ci, de + 512, dt);
#pragma unroll
        for (int k = 1; k < 4; k++) {
          mma_ss64<0, 1, 1>(ci, de + k * 2, dt + k * 128);
          mma_ss64<32, 1, 1>(ci, de + (512 + k * 2), dt + k * 128);
        }
      }
      wg_commit();

      auto head = [&](auto off, int t) {
        constexpr int O = decltype(off)::value;
        mbar_wait(bars + 8 * (B_FT + (t & 3)), t >> 2);
        const uint64_t db = d128(dN + (t & 3) * (TB >> 4));
        wg_fence();
        mma_rs64<O, 1, 0>(ct, h[0], h[1], h[2], h[3], db);
#pragma unroll
        for (int k = 1; k < 6; k++) mma_rs64<O, 1, 1>(ct, h[4 * k], h[4 * k + 1], h[4 * k + 2], h[4 * k + 3], db + k * 128);
        wg_commit();
        wg_wait<1>();
      };
      auto rest = [&](auto off, int t) {
        constexpr int O = decltype(off)::value;
        const uint64_t db = d128(dN + (t & 3) * (TB >> 4));
        wg_fence();
#pragma unroll
        for (int k = 6; k < 14; k++) mma_rs64<O, 1, 1>(ct, h[4 * k], h[4 * k + 1], h[4 * k + 2], h[4 * k + 3], db + k * 128);
#pragma unroll
        for (int k = 0; k < 4; k++) mma_rs64<O, 1, 1>(ct, yf[4 * k], yf[4 * k + 1], yf[4 * k + 2], yf[4 * k + 3], db + (14 + k) * 128);
        wg_commit();
      };
      auto freeT = [&](int t) { if (elect) mbar_arrive(bars + 8 * (B_ET + t)); };
      const uint32_t peerZ = mapa(sb + OFF_Z + tid * 16, rank ^ 1), peerB = mapa(bars + 8 * B_Z, rank ^ 1);
      auto send_peer = [&](auto off, int z) {
        constexpr int O = decltype(off)::value;
        fence_regs<O, 32>(ct);
#pragma unroll
        for (int i = 0; i < 4; i++)
          asm volatile("st.async.weak.shared::cluster.mbarrier::complete_tx::bytes.v4.b32 [%0], {%1,%2,%3,%4}, [%5];" ::"r"(peerZ + z * U + i * 4096),
                       "r"(pack_bf16(ct[O + 8 * i], ct[O + 8 * i + 1])), "r"(pack_bf16(ct[O + 8 * i + 2], ct[O + 8 * i + 3])),
                       "r"(pack_bf16(ct[O + 8 * i + 4], ct[O + 8 * i + 5])), "r"(pack_bf16(ct[O + 8 * i + 6], ct[O + 8 * i + 7])), "r"(peerB + 8 * z) : "memory");
      };
      auto send_grid = [&](auto off, int z) {
        constexpr int O = decltype(off)::value;
        fence_regs<O, 32>(ct);
        mbar_wait(bars + 8 * (B_Z + z), 0);
        uint4* dst = g_part + (size_t)((rb * 8 + 2 * ((q4 + z + 1) & 3) + rank) * 3 + z) * 1024 + tid;
#pragma unroll
        for (int i = 0; i < 4; i++) {
          const uint4 p = *(const uint4*)(smem + OFF_Z + z * U + i * 4096 + tid * 16);
          st_x4(dst + i * 256, (pack_bf16(ct[O + 8 * i] + bf_lo(p.x), ct[O + 8 * i + 1] + bf_hi(p.x)) & ~1u) | tag,
                pack_bf16(ct[O + 8 * i + 2] + bf_lo(p.y), ct[O + 8 * i + 3] + bf_hi(p.y)),
                pack_bf16(ct[O + 8 * i + 4] + bf_lo(p.z), ct[O + 8 * i + 5] + bf_hi(p.z)),
                pack_bf16(ct[O + 8 * i + 6] + bf_lo(p.w), ct[O + 8 * i + 7] + bf_hi(p.w)));
        }
        __syncwarp();
        if (lane == 0) hint_add(&g_cntP[32 * (rb * 8 + 2 * ((q4 + z + 1) & 3) + rank) + z]);
      };
      asm volatile("barrier.cluster.wait.aligned;" ::: "memory");
      head(IC<0>(), 0);
      if (elect) asm volatile("mbarrier.arrive.shared::cluster.b64 _, [%0];" ::"r"(mapa(bars + 8 * B_RDY, rank ^ 1)) : "memory");
      fence_regs<0, 64>(ci);
#pragma unroll
      for (int i = 0; i < 16; i++) {
        const float gg = ((i & 1) ? g1 : g0) * (2.0f / (2048.0f * 512.0f));
        yf[i] = pack_pin((ci[2 * i] + ci[33 + 2 * i]) * gg, (ci[2 * i + 1] - ci[32 + 2 * i]) * gg);
      }
      rest(IC<0>(), 0);
      if (tid == 0) PROF_EV(8);
      head(IC<32>(), 1); freeT(0); mbar_wait(bars + 8 * B_RDY, 0); send_peer(IC<0>(), 0); rest(IC<32>(), 1);
      head(IC<0>(), 2); freeT(1); send_peer(IC<32>(), 1); rest(IC<0>(), 2);
      head(IC<32>(), 3); freeT(2); send_peer(IC<0>(), 2); rest(IC<32>(), 3);
      head(IC<0>(), 4); freeT(3); send_grid(IC<32>(), 0); rest(IC<0>(), 4);
      head(IC<32>(), 5); send_grid(IC<0>(), 1); rest(IC<32>(), 5);
      head(IC<0>(), 6); send_grid(IC<32>(), 2); rest(IC<0>(), 6);
      head(IC<32>(), 7); send_peer(IC<0>(), 3);
      {
        const uint4* src = g_part + (size_t)(rb * 8 + j) * 3 * 1024 + tid;
        uint4 pv[12];
        mbar_wait(bars + 8 * (B_HP + 1), 0);
#pragma unroll
        for (int i = 0; i < 8; i++) pv[i] = ld_x4(src + i * 256);
        rest(IC<32>(), 7);
        if (tid == 0) PROF_EV(9);
        mbar_wait(bars + 8 * (B_HP + 2), 0);
        if (tid == 0) PROF_EV(24);
#pragma unroll
        for (int i = 8; i < 12; i++) pv[i] = ld_x4(src + i * 256);
        const uint32_t t0 = (uint32_t)clock();
        for (;;) {
          uint32_t bad = 0;
#pragma unroll
          for (int i = 0; i < 12; i++) bad |= pv[i].x ^ tag;
          if (!__any_sync(0xffffffffu, bad & 1)) break;
#pragma unroll
          for (int i = 0; i < 12; i++) pv[i] = ld_x4(src + i * 256);
          spin_guard(t0);
        }
        if (tid == 0) PROF_EV(14);
        float sum[32];
#pragma unroll
        for (int i = 0; i < 4; i++) {
          const uint32_t a[4] = {pv[i].x & ~1u, pv[i].y, pv[i].z, pv[i].w}, b[4] = {pv[4 + i].x & ~1u, pv[4 + i].y, pv[4 + i].z, pv[4 + i].w},
                         c[4] = {pv[8 + i].x & ~1u, pv[8 + i].y, pv[8 + i].z, pv[8 + i].w};
#pragma unroll
          for (int e = 0; e < 4; e++) {
            sum[8 * i + 2 * e] = bf_lo(a[e]) + bf_lo(b[e]) + bf_lo(c[e]);
            sum[8 * i + 2 * e + 1] = bf_hi(a[e]) + bf_hi(b[e]) + bf_hi(c[e]);
          }
        }
        mbar_wait(bars + 8 * (B_Z + 3), 0);
#pragma unroll
        for (int i = 0; i < 4; i++) {
          const uint4 p = *(const uint4*)(smem + OFF_Z + 3 * U + i * 4096 + tid * 16);
          const uint32_t a[4] = {p.x, p.y, p.z, p.w};
#pragma unroll
          for (int e = 0; e < 4; e++) { sum[8 * i + 2 * e] += bf_lo(a[e]); sum[8 * i + 2 * e + 1] += bf_hi(a[e]); }
        }
        wg_wait<0>();
        fence_regs<32, 32>(ct);
#pragma unroll
        for (int i = 0; i < 32; i++) sum[i] += ct[32 + i];
        const uint32_t stg = sb + OFF_T + warp * 2048;
        const int mr = (lane & 7) + ((lane >> 3) & 1) * 8, mc = lane >> 4;
#pragma unroll
        for (int i = 0; i < 4; i++) {
          const uint32_t a = stg + mr * 128 + (((2 * i + mc) ^ (mr & 7)) << 4);
          asm volatile("stmatrix.sync.aligned.m8n8.x4.shared.b16 [%0], {%1,%2,%3,%4};" ::"r"(a), "r"(pack_bf16(sum[8 * i], sum[8 * i + 1])),
                       "r"(pack_bf16(sum[8 * i + 2], sum[8 * i + 3])), "r"(pack_bf16(sum[8 * i + 4], sum[8 * i + 5])),
                       "r"(pack_bf16(sum[8 * i + 6], sum[8 * i + 7])) : "memory");
        }
        __syncwarp();
#pragma unroll
        for (int i = 0; i < 4; i++) {
          const int r = 4 * i + (lane >> 3), c = lane & 7;
          const uint4 v = *(const uint4*)(smem + OFF_T + warp * 2048 + r * 128 + ((c ^ (r & 7)) << 4));
          *(uint4*)(out + (size_t)(2 * rb + wg + 32 * (16 * w + r)) * 512 + 64 * j + 8 * c) = v;
        }
      }
      if (tid == 0) { g_epoch[blockIdx.x * 8] = ep + 1; PROF_EV(15); PROF_CK(41); }
    }
  }
}

typedef CUresult (*EncodeFn)(CUtensorMap*, CUtensorMapDataType, cuuint32_t, void*, const cuuint64_t*, const cuuint64_t*, const cuuint32_t*,
                             const cuuint32_t*, CUtensorMapInterleave, CUtensorMapSwizzle, CUtensorMapL2promotion, CUtensorMapFloatOOBfill);

static void encode(EncodeFn f, CUtensorMap* m, const void* base, int rank, const cuuint64_t* dims, const cuuint64_t* strides, const cuuint32_t* box,
                   CUtensorMapSwizzle sw) {
  cuuint32_t es[5] = {1, 1, 1, 1, 1};
  f(m, CU_TENSOR_MAP_DATA_TYPE_BFLOAT16, rank, (void*)base, dims, strides, box, es, CU_TENSOR_MAP_INTERLEAVE_NONE, sw,
    CU_TENSOR_MAP_L2_PROMOTION_L2_128B, CU_TENSOR_MAP_FLOAT_OOB_FILL_NONE);
}

extern "C" void kernel_launch(void* const* d_in, const int* in_sizes, int n_in, void* d_out, int out_size) {
  (void)in_sizes; (void)n_in; (void)out_size;
  const __nv_bfloat16* x = (const __nv_bfloat16*)d_in[0];
  const __nv_bfloat16* w_r = (const __nv_bfloat16*)d_in[1];
  const __nv_bfloat16* w_i = (const __nv_bfloat16*)d_in[2];
  const __nv_bfloat16* Wg = (const __nv_bfloat16*)d_in[4];
  const __nv_bfloat16* Wu = (const __nv_bfloat16*)d_in[5];
  const __nv_bfloat16* Wd = (const __nv_bfloat16*)d_in[6];
  const __nv_bfloat16* gw = (const __nv_bfloat16*)d_in[7];

  void* fp = nullptr; cudaDriverEntryPointQueryResult qr;
  cudaGetDriverEntryPoint("cuTensorMapEncodeTiled", &fp, cudaEnableDefault, &qr);
  EncodeFn enc = (EncodeFn)fp;
  void *pFT, *pET;
  cudaGetSymbolAddress(&pFT, g_FT); cudaGetSymbolAddress(&pET, g_ET);

  Maps mp;
  const CUtensorMapSwizzle S128 = CU_TENSOR_MAP_SWIZZLE_128B, S64 = CU_TENSOR_MAP_SWIZZLE_64B;
  { cuuint64_t d[3] = {512, 64, 32}, s[2] = {32768, 1024}; cuuint32_t b[3] = {64, 64, 2}; encode(enc, &mp.x, x, 3, d, s, b, S128); }
  { cuuint64_t d[2] = {512, 512}, s[1] = {1024}; cuuint32_t b[2] = {64, 64}; encode(enc, &mp.ft, pFT, 2, d, s, b, S128); }
  { cuuint64_t d[4] = {512, 2, 8, 32}, s[3] = {8192, 1024, 16384}; cuuint32_t b[4] = {64, 2, 8, 4}; encode(enc, &mp.fg, pFT, 4, d, s, b, S128); }
  { cuuint64_t d[4] = {64, 64, 2, 32}, s[3] = {8192, 128, 256}; cuuint32_t b[4] = {64, 64, 2, 1}; encode(enc, &mp.e, pET, 4, d, s, b, S128); }
  { cuuint64_t d[2] = {1792, 512}, s[1] = {3584}; cuuint32_t b[2] = {64, 64}, b2[2] = {32, 64};
    encode(enc, &mp.g64, Wg, 2, d, s, b, S128); encode(enc, &mp.u64, Wu, 2, d, s, b, S128);
    encode(enc, &mp.g32, Wg, 2, d, s, b2, S64); encode(enc, &mp.u32, Wu, 2, d, s, b2, S64); }
  { cuuint64_t d[2] = {512, 1792}, s[1] = {1024}; cuuint32_t b[2] = {64, 192}, b2[2] = {64, 32};
    encode(enc, &mp.d192, Wd, 2, d, s, b, S128); encode(enc, &mp.d32, Wd, 2, d, s, b2, S128); }

  cudaFuncSetAttribute(fused_kernel, cudaFuncAttributeMaxDynamicSharedMemorySize, SMEM_BYTES);
  fused_kernel<<<NCTA, 512, SMEM_BYTES>>>(mp, x, w_r, w_i, gw, Wg, Wu, (__nv_bfloat16*)d_out);
}
```

```cpp
#include <cuda_runtime.h>
#include <cuda_bf16.h>
#include <cuda.h>
#include <stdint.h>

namespace tbl {
constexpr double PI = 3.14159265358979323846264338327950288;
constexpr double sin_s(double x) { double t = x, s = x; for (int n = 1; n < 12; n++) { t *= -x * x / ((2 * n) * (2 * n + 1)); s += t; } return s; }
constexpr double cos_s(double x) { double t = 1, s = 1; for (int n = 1; n < 12; n++) { t *= -x * x / ((2 * n - 1) * (2 * n)); s += t; } return s; }
constexpr double cos2048(int m) {
  m &= 2047; if (m > 1024) m = 2048 - m;
  bool neg = false; if (m > 512) { m = 1024 - m; neg = true; }
  double v = (m <= 256) ? cos_s(2 * PI * m / 2048) : sin_s(2 * PI * (512 - m) / 2048);
  return neg ? -v : v;
}
constexpr uint16_t to_bf16(double v) {
  if (v == 0) return 0;
  uint16_t s = 0; if (v < 0) { s = 0x8000; v = -v; }
  int e = 0; while (v >= 2) { v /= 2; e++; } while (v < 1) { v *= 2; e--; }
  double m = (v - 1) * 128; int mi = (int)m; double fr = m - mi;
  if (fr > 0.5 || (fr == 0.5 && (mi & 1))) mi++;
  if (mi == 128) { mi = 0; e++; }
  return (uint16_t)(s | ((e + 127) << 7) | mi);
}
struct CosT { uint16_t v[2048]; constexpr CosT() : v() { for (int i = 0; i < 2048; i++) v[i] = to_bf16(cos2048(i)); } };
struct alignas(1024) FT {
  uint16_t v[512 * 512];
  constexpr FT() : v() {
    CosT c;
    for (int r = 0; r < 512; r++) {
      int k = (r >> 4) * 8 + (r & 7), e = (r >> 3) & 1;
      int mul = 4 * k, add = e ? 512 : 0;
      if (k == 0 && e == 1) { mul = 1024; add = 0; }
      for (int d = 0; d < 512; d++) v[r * 512 + d] = c.v[(d * mul + add) & 2047];
    }
  }
};
struct alignas(1024) ET {
  uint16_t v[2048 * 128];
  constexpr ET() : v() {
    CosT c;
    for (int s = 0; s < 2048; s++)
      for (int j = 0; j < 64; j++) { v[s * 128 + j] = c.v[(s * j) & 2047]; v[s * 128 + 64 + j] = c.v[(s * j + 512) & 2047]; }
  }
};
struct alignas(1024) DT {
  uint16_t v[64 * 64];
  constexpr DT() : v() {
    CosT c;
    for (int r = 0; r < 64; r++)
      for (int n = 0; n < 64; n++) {
        const int sg = r >> 1, s0 = (sg & ~6) | ((sg & 2) << 1) | ((sg & 4) >> 1), e = r & 1, f = n & 1;
        const int m = 64 * s0 * (n >> 1) + (e == f ? 0 : e ? -512 : 512);
        v[r * 64 + (((n >> 3) ^ (r & 7)) << 3) + (n & 7)] = c.v[m & 2047];
      }
  }
};
}

__device__ constexpr tbl::FT g_FT = tbl::FT();
__device__ constexpr tbl::ET g_ET = tbl::ET();
__device__ constexpr tbl::DT g_DT = tbl::DT();

__device__ __align__(1024) uint16_t g_X[129 * 8192];
__device__ __align__(1024) uint16_t g_T[32 * 64 * 512];
__device__ __align__(1024) uint2 g_Ts[32 * 64];
__device__ __align__(1024) uint4 g_part[128 * 3 * 1024];
__device__ __align__(16) float g_gate[16 * 128];
__device__ __align__(16) uint2 g_Wh[2 * 2048];
__device__ unsigned g_epoch[132 * 8];
__device__ unsigned g_cntX[8 * 32], g_cntT[8 * 32], g_cntP[128 * 32], g_cntW[32], g_cntH[32];
#define PROF_EV(i) do {} while (0)
#define PROF_CK(i) do {} while (0)

__device__ __forceinline__ uint32_t smem_u32(const void* p) { return (uint32_t)__cvta_generic_to_shared(p); }
__device__ __forceinline__ void mbar_init(uint32_t bar, uint32_t cnt) { asm volatile("mbarrier.init.shared::cta.b64 [%0], %1;" ::"r"(bar), "r"(cnt)); }
__device__ __forceinline__ void mbar_expect_tx(uint32_t bar, uint32_t bytes) { asm volatile("mbarrier.arrive.expect_tx.shared::cta.b64 _, [%0], %1;" ::"r"(bar), "r"(bytes) : "memory"); }
__device__ __forceinline__ void mbar_arrive(uint32_t bar) { asm volatile("mbarrier.arrive.shared::cta.b64 _, [%0];" ::"r"(bar) : "memory"); }
__device__ __forceinline__ void mbar_wait(uint32_t bar, uint32_t parity) {
  asm volatile(
      "{\n.reg .pred p;\n.reg .u32 n;\nmov.u32 n, 0;\n"
      "W_LOOP:\nmbarrier.try_wait.parity.shared::cta.b64 p, [%0], %1;\n@p bra W_DONE;\n"
      "add.u32 n, n, 1;\nsetp.lt.u32 p, n, 0x40000;\n@p bra W_LOOP;\ntrap;\nW_DONE:\n}" ::"r"(bar), "r"(parity) : "memory");
}
__device__ __forceinline__ void bulk_load(uint32_t dst, const void* src, uint32_t bytes, uint32_t bar) {
  asm volatile("cp.async.bulk.shared::cluster.global.mbarrier::complete_tx::bytes [%0], [%1], %2, [%3];" ::"r"(dst), "l"(src), "r"(bytes), "r"(bar) : "memory");
}
__device__ __forceinline__ void cp16(uint32_t dst, const void* src) { asm volatile("cp.async.cg.shared.global [%0], [%1], 16;" ::"r"(dst), "l"(src) : "memory"); }
__device__ __forceinline__ void spin_guard(uint32_t t0) { if ((uint32_t)clock() - t0 > (1u << 30)) __trap(); }
__device__ __forceinline__ float tagf(float v, uint32_t tag) { return __uint_as_float((__float_as_uint(v) & ~1u) | tag); }
__device__ __forceinline__ float untag(float v) { return __uint_as_float(__float_as_uint(v) & ~1u); }
__device__ __forceinline__ void st_x2(float2* p, float a, float b) { asm volatile("st.relaxed.gpu.global.v2.f32 [%0], {%1,%2};" ::"l"(p), "f"(a), "f"(b) : "memory"); }
__device__ __forceinline__ float2 ld_x2(const float2* p) { float2 v; asm volatile("ld.relaxed.gpu.global.v2.f32 {%0,%1}, [%2];" : "=f"(v.x), "=f"(v.y) : "l"(p) : "memory"); return v; }
__device__ __forceinline__ void st_u2(uint2* p, uint32_t a, uint32_t b) { asm volatile("st.relaxed.gpu.global.v2.u32 [%0], {%1,%2};" ::"l"(p), "r"(a), "r"(b) : "memory"); }
__device__ __forceinline__ void prefetch2d(const CUtensorMap* m, int c0, int c1) { asm volatile("cp.async.bulk.prefetch.tensor.2d.L2.global [%0, {%1, %2}];" ::"l"(m), "r"(c0), "r"(c1) : "memory"); }
__device__ __forceinline__ void prefetch1d(const void* p, uint32_t bytes) { asm volatile("cp.async.bulk.prefetch.L2.global [%0], %1;" ::"l"(p), "r"(bytes) : "memory"); }
__device__ __forceinline__ uint32_t ld_x1(const void* p) { uint32_t v; asm volatile("ld.relaxed.gpu.global.u32 %0, [%1];" : "=r"(v) : "l"(p) : "memory"); return v; }
__device__ __forceinline__ uint4 ld_x4(const void* p) { uint4 v; asm volatile("ld.relaxed.gpu.global.v4.u32 {%0,%1,%2,%3}, [%4];" : "=r"(v.x), "=r"(v.y), "=r"(v.z), "=r"(v.w) : "l"(p) : "memory"); return v; }
__device__ __forceinline__ void st_x4(void* p, uint32_t a, uint32_t b, uint32_t c, uint32_t d) { asm volatile("st.relaxed.gpu.global.v4.u32 [%0], {%1,%2,%3,%4};" ::"l"(p), "r"(a), "r"(b), "r"(c), "r"(d) : "memory"); }
__device__ __forceinline__ uint32_t mapa(uint32_t a, uint32_t cta) { uint32_t r; asm volatile("mapa.shared::cluster.u32 %0, %1, %2;" : "=r"(r) : "r"(a), "r"(cta)); return r; }
__device__ __forceinline__ void flag_release(unsigned* p) { asm volatile("red.release.gpu.global.add.u32 [%0], 1;" ::"l"(p) : "memory"); }
__device__ __forceinline__ void flag_acquire(const unsigned* p, unsigned target) {
  const uint32_t t0 = (uint32_t)clock();
  for (;;) {
    unsigned v;
    asm volatile("ld.acquire.gpu.global.u32 %0, [%1];" : "=r"(v) : "l"(p) : "memory");
    if ((int)(v - target) >= 0) break;
    spin_guard(t0);
  }
  asm volatile("fence.proxy.async;" ::: "memory");
}
__device__ __forceinline__ void bulk_done_release(unsigned* p) {
  asm volatile("cp.async.bulk.commit_group;\ncp.async.bulk.wait_group 0;\nfence.proxy.async;" ::: "memory");
  flag_release(p);
}
__device__ __forceinline__ void stsm4t(uint32_t a, uint32_t r0, uint32_t r1, uint32_t r2, uint32_t r3) {
  asm volatile("stmatrix.sync.aligned.m8n8.x4.trans.shared.b16 [%0], {%1,%2,%3,%4};" ::"r"(a), "r"(r0), "r"(r1), "r"(r2), "r"(r3) : "memory");
}
__device__ __forceinline__ void hint_add(unsigned* p) { asm volatile("red.relaxed.gpu.global.add.u32 [%0], 1;" ::"l"(p) : "memory"); }
__device__ __forceinline__ void hint_wait(const unsigned* p, unsigned target) {
  const uint32_t t0 = (uint32_t)clock();
  while ((int)(ld_x1(p) - target) < 0) spin_guard(t0);
}
__device__ __forceinline__ void tma2d(uint32_t dst, const CUtensorMap* m, uint32_t bar, int c0, int c1) {
  asm volatile("cp.async.bulk.tensor.2d.shared::cluster.global.mbarrier::complete_tx::bytes [%0], [%1, {%3, %4}], [%2];" ::"r"(dst), "l"(m), "r"(bar), "r"(c0), "r"(c1) : "memory");
}
__device__ __forceinline__ void tma3d(uint32_t dst, const CUtensorMap* m, uint32_t bar, int c0, int c1, int c2) {
  asm volatile("cp.async.bulk.tensor.3d.shared::cluster.global.mbarrier::complete_tx::bytes [%0], [%1, {%3, %4, %5}], [%2];" ::"r"(dst), "l"(m), "r"(bar), "r"(c0), "r"(c1), "r"(c2) : "memory");
}
__device__ __forceinline__ void tma4d(uint32_t dst, const CUtensorMap* m, uint32_t bar, int c0, int c1, int c2, int c3) {
  asm volatile("cp.async.bulk.tensor.4d.shared::cluster.global.mbarrier::complete_tx::bytes [%0], [%1, {%3, %4, %5, %6}], [%2];" ::"r"(dst), "l"(m), "r"(bar), "r"(c0), "r"(c1), "r"(c2), "r"(c3) : "memory");
}
__device__ __forceinline__ void wg_fence() { asm volatile("wgmma.fence.sync.aligned;" ::: "memory"); }
__device__ __forceinline__ void wg_commit() { asm volatile("wgmma.commit_group.sync.aligned;" ::: "memory"); }
template <int N> __device__ __forceinline__ void wg_wait() { asm volatile("wgmma.wait_group.sync.aligned %0;" ::"n"(N) : "memory"); }
template <int O, int N, int NN> __device__ __forceinline__ void fence_regs(float (&d)[NN]) {
#pragma unroll
  for (int i = 0; i < N; i++) asm volatile("" : "+f"(d[O + i])::"memory");
}
__device__ __forceinline__ uint32_t pack_bf16(float lo, float hi) {
  uint32_t r; asm("cvt.rn.bf16x2.f32 %0, %1, %2;" : "=r"(r) : "f"(hi), "f"(lo)); return r;
}
__device__ __forceinline__ uint32_t pack_pin(float lo, float hi) {
  uint32_t r; asm volatile("cvt.rn.bf16x2.f32 %0, %1, %2;" : "=r"(r) : "f"(hi), "f"(lo) : "memory"); return r;
}
__device__ __forceinline__ float bf_lo(uint32_t u) { return __uint_as_float(u << 16); }
__device__ __forceinline__ float bf_hi(uint32_t u) { return __uint_as_float(u & 0xffff0000u); }

__device__ __forceinline__ uint64_t d128(uint32_t lo) { uint64_t d; asm("mov.b64 %0, {%1, 0x40000040};" : "=l"(d) : "r"(lo)); return d; }
__device__ __forceinline__ uint64_t d64(uint32_t lo) { uint64_t d; asm("mov.b64 %0, {%1, 0x80000020};" : "=l"(d) : "r"(lo)); return d; }
template<int O,int TB,int ACC,int NN> __device__ __forceinline__ void mma_ss64(float (&d)[NN], uint64_t da, uint64_t db, int sd = 0){
  if constexpr (ACC == 1) asm volatile("wgmma.mma_async.sync.aligned.m64n64k16.f32.bf16.bf16 {%0,%1,%2,%3,%4,%5,%6,%7,%8,%9,%10,%11,%12,%13,%14,%15,%16,%17,%18,%19,%20,%21,%22,%23,%24,%25,%26,%27,%28,%29,%30,%31}, %32, %33, 1, 1, 1, %35, %34;"
   : "+f"(d[O+0]), "+f"(d[O+1]), "+f"(d[O+2]), "+f"(d[O+3]), "+f"(d[O+4]), "+f"(d[O+5]), "+f"(d[O+6]), "+f"(d[O+7]), "+f"(d[O+8]), "+f"(d[O+9]), "+f"(d[O+10]), "+f"(d[O+11]), "+f"(d[O+12]), "+f"(d[O+13]), "+f"(d[O+14]), "+f"(d[O+15]), "+f"(d[O+16]), "+f"(d[O+17]), "+f"(d[O+18]), "+f"(d[O+19]), "+f"(d[O+20]), "+f"(d[O+21]), "+f"(d[O+22]), "+f"(d[O+23]), "+f"(d[O+24]), "+f"(d[O+25]), "+f"(d[O+26]), "+f"(d[O+27]), "+f"(d[O+28]), "+f"(d[O+29]), "+f"(d[O+30]), "+f"(d[O+31])
   : "l"(da), "l"(db), "n"(TB & 1), "n"(TB >> 1));
  else if constexpr (ACC == 0) asm volatile("wgmma.mma_async.sync.aligned.m64n64k16.f32.bf16.bf16 {%0,%1,%2,%3,%4,%5,%6,%7,%8,%9,%10,%11,%12,%13,%14,%15,%16,%17,%18,%19,%20,%21,%22,%23,%24,%25,%26,%27,%28,%29,%30,%31}, %32, %33, 0, 1, 1, %35, %34;"
   : "=f"(d[O+0]), "=f"(d[O+1]), "=f"(d[O+2]), "=f"(d[O+3]), "=f"(d[O+4]), "=f"(d[O+5]), "=f"(d[O+6]), "=f"(d[O+7]), "=f"(d[O+8]), "=f"(d[O+9]), "=f"(d[O+10]), "=f"(d[O+11]), "=f"(d[O+12]), "=f"(d[O+13]), "=f"(d[O+14]), "=f"(d[O+15]), "=f"(d[O+16]), "=f"(d[O+17]), "=f"(d[O+18]), "=f"(d[O+19]), "=f"(d[O+20]), "=f"(d[O+21]), "=f"(d[O+22]), "=f"(d[O+23]), "=f"(d[O+24]), "=f"(d[O+25]), "=f"(d[O+26]), "=f"(d[O+27]), "=f"(d[O+28]), "=f"(d[O+29]), "=f"(d[O+30]), "=f"(d[O+31])
   : "l"(da), "l"(db), "n"(TB & 1), "n"(TB >> 1));
  else asm volatile("{\n.reg .pred p;\nsetp.ne.b32 p, %36, 0;\nwgmma.mma_async.sync.aligned.m64n64k16.f32.bf16.bf16 {%0,%1,%2,%3,%4,%5,%6,%7,%8,%9,%10,%11,%12,%13,%14,%15,%16,%17,%18,%19,%20,%21,%22,%23,%24,%25,%26,%27,%28,%29,%30,%31}, %32, %33, p, 1, 1, %35, %34;\n}"
   : "+f"(d[O+0]), "+f"(d[O+1]), "+f"(d[O+2]), "+f"(d[O+3]), "+f"(d[O+4]), "+f"(d[O+5]), "+f"(d[O+6]), "+f"(d[O+7]), "+f"(d[O+8]), "+f"(d[O+9]), "+f"(d[O+10]), "+f"(d[O+11]), "+f"(d[O+12]), "+f"(d[O+13]), "+f"(d[O+14]), "+f"(d[O+15]), "+f"(d[O+16]), "+f"(d[O+17]), "+f"(d[O+18]), "+f"(d[O+19]), "+f"(d[O+20]), "+f"(d[O+21]), "+f"(d[O+22]), "+f"(d[O+23]), "+f"(d[O+24]), "+f"(d[O+25]), "+f"(d[O+26]), "+f"(d[O+27]), "+f"(d[O+28]), "+f"(d[O+29]), "+f"(d[O+30]), "+f"(d[O+31])
   : "l"(da), "l"(db), "n"(TB & 1), "n"(TB >> 1), "r"(sd));
}
template<int O,int TB,int ACC,int NN> __device__ __forceinline__ void mma_rs64(float (&d)[NN], uint32_t a0, uint32_t a1, uint32_t a2, uint32_t a3, uint64_t db, int sd = 0){
  if constexpr (ACC == 1) asm volatile("wgmma.mma_async.sync.aligned.m64n64k16.f32.bf16.bf16 {%0,%1,%2,%3,%4,%5,%6,%7,%8,%9,%10,%11,%12,%13,%14,%15,%16,%17,%18,%19,%20,%21,%22,%23,%24,%25,%26,%27,%28,%29,%30,%31}, {%32,%33,%34,%35}, %36, 1, 1, 1, %37;"
   : "+f"(d[O+0]), "+f"(d[O+1]), "+f"(d[O+2]), "+f"(d[O+3]), "+f"(d[O+4]), "+f"(d[O+5]), "+f"(d[O+6]), "+f"(d[O+7]), "+f"(d[O+8]), "+f"(d[O+9]), "+f"(d[O+10]), "+f"(d[O+11]), "+f"(d[O+12]), "+f"(d[O+13]), "+f"(d[O+14]), "+f"(d[O+15]), "+f"(d[O+16]), "+f"(d[O+17]), "+f"(d[O+18]), "+f"(d[O+19]), "+f"(d[O+20]), "+f"(d[O+21]), "+f"(d[O+22]), "+f"(d[O+23]), "+f"(d[O+24]), "+f"(d[O+25]), "+f"(d[O+26]), "+f"(d[O+27]), "+f"(d[O+28]), "+f"(d[O+29]), "+f"(d[O+30]), "+f"(d[O+31])
   : "r"(a0), "r"(a1), "r"(a2), "r"(a3), "l"(db), "n"(TB));
  else if constexpr (ACC == 0) asm volatile("wgmma.mma_async.sync.aligned.m64n64k16.f32.bf16.bf16 {%0,%1,%2,%3,%4,%5,%6,%7,%8,%9,%10,%11,%12,%13,%14,%15,%16,%17,%18,%19,%20,%21,%22,%23,%24,%25,%26,%27,%28,%29,%30,%31}, {%32,%33,%34,%35}, %36, 0, 1, 1, %37;"
   : "=f"(d[O+0]), "=f"(d[O+1]), "=f"(d[O+2]), "=f"(d[O+3]), "=f"(d[O+4]), "=f"(d[O+5]), "=f"(d[O+6]), "=f"(d[O+7]), "=f"(d[O+8]), "=f"(d[O+9]), "=f"(d[O+10]), "=f"(d[O+11]), "=f"(d[O+12]), "=f"(d[O+13]), "=f"(d[O+14]), "=f"(d[O+15]), "=f"(d[O+16]), "=f"(d[O+17]), "=f"(d[O+18]), "=f"(d[O+19]), "=f"(d[O+20]), "=f"(d[O+21]), "=f"(d[O+22]), "=f"(d[O+23]), "=f"(d[O+24]), "=f"(d[O+25]), "=f"(d[O+26]), "=f"(d[O+27]), "=f"(d[O+28]), "=f"(d[O+29]), "=f"(d[O+30]), "=f"(d[O+31])
   : "r"(a0), "r"(a1), "r"(a2), "r"(a3), "l"(db), "n"(TB));
  else asm volatile("{\n.reg .pred p;\nsetp.ne.b32 p, %38, 0;\nwgmma.mma_async.sync.aligned.m64n64k16.f32.bf16.bf16 {%0,%1,%2,%3,%4,%5,%6,%7,%8,%9,%10,%11,%12,%13,%14,%15,%16,%17,%18,%19,%20,%21,%22,%23,%24,%25,%26,%27,%28,%29,%30,%31}, {%32,%33,%34,%35}, %36, p, 1, 1, %37;\n}"
   : "+f"(d[O+0]), "+f"(d[O+1]), "+f"(d[O+2]), "+f"(d[O+3]), "+f"(d[O+4]), "+f"(d[O+5]), "+f"(d[O+6]), "+f"(d[O+7]), "+f"(d[O+8]), "+f"(d[O+9]), "+f"(d[O+10]), "+f"(d[O+11]), "+f"(d[O+12]), "+f"(d[O+13]), "+f"(d[O+14]), "+f"(d[O+15]), "+f"(d[O+16]), "+f"(d[O+17]), "+f"(d[O+18]), "+f"(d[O+19]), "+f"(d[O+20]), "+f"(d[O+21]), "+f"(d[O+22]), "+f"(d[O+23]), "+f"(d[O+24]), "+f"(d[O+25]), "+f"(d[O+26]), "+f"(d[O+27]), "+f"(d[O+28]), "+f"(d[O+29]), "+f"(d[O+30]), "+f"(d[O+31])
   : "r"(a0), "r"(a1), "r"(a2), "r"(a3), "l"(db), "n"(TB), "r"(sd));
}
template<int O,int TB,int ACC,int NN> __device__ __forceinline__ void mma_ss128(float (&d)[NN], uint64_t da, uint64_t db, int sd = 0){
  if constexpr (ACC == 1) asm volatile("wgmma.mma_async.sync.aligned.m64n128k16.f32.bf16.bf16 {%0,%1,%2,%3,%4,%5,%6,%7,%8,%9,%10,%11,%12,%13,%14,%15,%16,%17,%18,%19,%20,%21,%22,%23,%24,%25,%26,%27,%28,%29,%30,%31,%32,%33,%34,%35,%36,%37,%38,%39,%40,%41,%42,%43,%44,%45,%46,%47,%48,%49,%50,%51,%52,%53,%54,%55,%56,%57,%58,%59,%60,%61,%62,%63}, %64, %65, 1, 1, 1, %67, %66;"
   : "+f"(d[O+0]), "+f"(d[O+1]), "+f"(d[O+2]), "+f"(d[O+3]), "+f"(d[O+4]), "+f"(d[O+5]), "+f"(d[O+6]), "+f"(d[O+7]), "+f"(d[O+8]), "+f"(d[O+9]), "+f"(d[O+10]), "+f"(d[O+11]), "+f"(d[O+12]), "+f"(d[O+13]), "+f"(d[O+14]), "+f"(d[O+15]), "+f"(d[O+16]), "+f"(d[O+17]), "+f"(d[O+18]), "+f"(d[O+19]), "+f"(d[O+20]), "+f"(d[O+21]), "+f"(d[O+22]), "+f"(d[O+23]), "+f"(d[O+24]), "+f"(d[O+25]), "+f"(d[O+26]), "+f"(d[O+27]), "+f"(d[O+28]), "+f"(d[O+29]), "+f"(d[O+30]), "+f"(d[O+31]), "+f"(d[O+32]), "+f"(d[O+33]), "+f"(d[O+34]), "+f"(d[O+35]), "+f"(d[O+36]), "+f"(d[O+37]), "+f"(d[O+38]), "+f"(d[O+39]), "+f"(d[O+40]), "+f"(d[O+41]), "+f"(d[O+42]), "+f"(d[O+43]), "+f"(d[O+44]), "+f"(d[O+45]), "+f"(d[O+46]), "+f"(d[O+47]), "+f"(d[O+48]), "+f"(d[O+49]), "+f"(d[O+50]), "+f"(d[O+51]), "+f"(d[O+52]), "+f"(d[O+53]), "+f"(d[O+54]), "+f"(d[O+55]), "+f"(d[O+56]), "+f"(d[O+57]), "+f"(d[O+58]), "+f"(d[O+59]), "+f"(d[O+60]), "+f"(d[O+61]), "+f"(d[O+62]), "+f"(d[O+63])
   : "l"(da), "l"(db), "n"(TB & 1), "n"(TB >> 1));
  else if constexpr (ACC == 0) asm volatile("wgmma.mma_async.sync.aligned.m64n128k16.f32.bf16.bf16 {%0,%1,%2,%3,%4,%5,%6,%7,%8,%9,%10,%11,%12,%13,%14,%15,%16,%17,%18,%19,%20,%21,%22,%23,%24,%25,%26,%27,%28,%29,%30,%31,%32,%33,%34,%35,%36,%37,%38,%39,%40,%41,%42,%43,%44,%45,%46,%47,%48,%49,%50,%51,%52,%53,%54,%55,%56,%57,%58,%59,%60,%61,%62,%63}, %64, %65, 0, 1, 1, %67, %66;"
   : "=f"(d[O+0]), "=f"(d[O+1]), "=f"(d[O+2]), "=f"(d[O+3]), "=f"(d[O+4]), "=f"(d[O+5]), "=f"(d[O+6]), "=f"(d[O+7]), "=f"(d[O+8]), "=f"(d[O+9]), "=f"(d[O+10]), "=f"(d[O+11]), "=f"(d[O+12]), "=f"(d[O+13]), "=f"(d[O+14]), "=f"(d[O+15]), "=f"(d[O+16]), "=f"(d[O+17]), "=f"(d[O+18]), "=f"(d[O+19]), "=f"(d[O+20]), "=f"(d[O+21]), "=f"(d[O+22]), "=f"(d[O+23]), "=f"(d[O+24]), "=f"(d[O+25]), "=f"(d[O+26]), "=f"(d[O+27]), "=f"(d[O+28]), "=f"(d[O+29]), "=f"(d[O+30]), "=f"(d[O+31]), "=f"(d[O+32]), "=f"(d[O+33]), "=f"(d[O+34]), "=f"(d[O+35]), "=f"(d[O+36]), "=f"(d[O+37]), "=f"(d[O+38]), "=f"(d[O+39]), "=f"(d[O+40]), "=f"(d[O+41]), "=f"(d[O+42]), "=f"(d[O+43]), "=f"(d[O+44]), "=f"(d[O+45]), "=f"(d[O+46]), "=f"(d[O+47]), "=f"(d[O+48]), "=f"(d[O+49]), "=f"(d[O+50]), "=f"(d[O+51]), "=f"(d[O+52]), "=f"(d[O+53]), "=f"(d[O+54]), "=f"(d[O+55]), "=f"(d[O+56]), "=f"(d[O+57]), "=f"(d[O+58]), "=f"(d[O+59]), "=f"(d[O+60]), "=f"(d[O+61]), "=f"(d[O+62]), "=f"(d[O+63])
   : "l"(da), "l"(db), "n"(TB & 1), "n"(TB >> 1));
  else asm volatile("{\n.reg .pred p;\nsetp.ne.b32 p, %68, 0;\nwgmma.mma_async.sync.aligned.m64n128k16.f32.bf16.bf16 {%0,%1,%2,%3,%4,%5,%6,%7,%8,%9,%10,%11,%12,%13,%14,%15,%16,%17,%18,%19,%20,%21,%22,%23,%24,%25,%26,%27,%28,%29,%30,%31,%32,%33,%34,%35,%36,%37,%38,%39,%40,%41,%42,%43,%44,%45,%46,%47,%48,%49,%50,%51,%52,%53,%54,%55,%56,%57,%58,%59,%60,%61,%62,%63}, %64, %65, p, 1, 1, %67, %66;\n}"
   : "+f"(d[O+0]), "+f"(d[O+1]), "+f"(d[O+2]), "+f"(d[O+3]), "+f"(d[O+4]), "+f"(d[O+5]), "+f"(d[O+6]), "+f"(d[O+7]), "+f"(d[O+8]), "+f"(d[O+9]), "+f"(d[O+10]), "+f"(d[O+11]), "+f"(d[O+12]), "+f"(d[O+13]), "+f"(d[O+14]), "+f"(d[O+15]), "+f"(d[O+16]), "+f"(d[O+17]), "+f"(d[O+18]), "+f"(d[O+19]), "+f"(d[O+20]), "+f"(d[O+21]), "+f"(d[O+22]), "+f"(d[O+23]), "+f"(d[O+24]), "+f"(d[O+25]), "+f"(d[O+26]), "+f"(d[O+27]), "+f"(d[O+28]), "+f"(d[O+29]), "+f"(d[O+30]), "+f"(d[O+31]), "+f"(d[O+32]), "+f"(d[O+33]), "+f"(d[O+34]), "+f"(d[O+35]), "+f"(d[O+36]), "+f"(d[O+37]), "+f"(d[O+38]), "+f"(d[O+39]), "+f"(d[O+40]), "+f"(d[O+41]), "+f"(d[O+42]), "+f"(d[O+43]), "+f"(d[O+44]), "+f"(d[O+45]), "+f"(d[O+46]), "+f"(d[O+47]), "+f"(d[O+48]), "+f"(d[O+49]), "+f"(d[O+50]), "+f"(d[O+51]), "+f"(d[O+52]), "+f"(d[O+53]), "+f"(d[O+54]), "+f"(d[O+55]), "+f"(d[O+56]), "+f"(d[O+57]), "+f"(d[O+58]), "+f"(d[O+59]), "+f"(d[O+60]), "+f"(d[O+61]), "+f"(d[O+62]), "+f"(d[O+63])
   : "l"(da), "l"(db), "n"(TB & 1), "n"(TB >> 1), "r"(sd));
}
template<int O,int TB,int ACC,int NN> __device__ __forceinline__ void mma_rs128(float (&d)[NN], uint32_t a0, uint32_t a1, uint32_t a2, uint32_t a3, uint64_t db, int sd = 0){
  if constexpr (ACC == 1) asm volatile("wgmma.mma_async.sync.aligned.m64n128k16.f32.bf16.bf16 {%0,%1,%2,%3,%4,%5,%6,%7,%8,%9,%10,%11,%12,%13,%14,%15,%16,%17,%18,%19,%20,%21,%22,%23,%24,%25,%26,%27,%28,%29,%30,%31,%32,%33,%34,%35,%36,%37,%38,%39,%40,%41,%42,%43,%44,%45,%46,%47,%48,%49,%50,%51,%52,%53,%54,%55,%56,%57,%58,%59,%60,%61,%62,%63}, {%64,%65,%66,%67}, %68, 1, 1, 1, %69;"
   : "+f"(d[O+0]), "+f"(d[O+1]), "+f"(d[O+2]), "+f"(d[O+3]), "+f"(d[O+4]), "+f"(d[O+5]), "+f"(d[O+6]), "+f"(d[O+7]), "+f"(d[O+8]), "+f"(d[O+9]), "+f"(d[O+10]), "+f"(d[O+11]), "+f"(d[O+12]), "+f"(d[O+13]), "+f"(d[O+14]), "+f"(d[O+15]), "+f"(d[O+16]), "+f"(d[O+17]), "+f"(d[O+18]), "+f"(d[O+19]), "+f"(d[O+20]), "+f"(d[O+21]), "+f"(d[O+22]), "+f"(d[O+23]), "+f"(d[O+24]), "+f"(d[O+25]), "+f"(d[O+26]), "+f"(d[O+27]), "+f"(d[O+28]), "+f"(d[O+29]), "+f"(d[O+30]), "+f"(d[O+31]), "+f"(d[O+32]), "+f"(d[O+33]), "+f"(d[O+34]), "+f"(d[O+35]), "+f"(d[O+36]), "+f"(d[O+37]), "+f"(d[O+38]), "+f"(d[O+39]), "+f"(d[O+40]), "+f"(d[O+41]), "+f"(d[O+42]), "+f"(d[O+43]), "+f"(d[O+44]), "+f"(d[O+45]), "+f"(d[O+46]), "+f"(d[O+47]), "+f"(d[O+48]), "+f"(d[O+49]), "+f"(d[O+50]), "+f"(d[O+51]), "+f"(d[O+52]), "+f"(d[O+53]), "+f"(d[O+54]), "+f"(d[O+55]), "+f"(d[O+56]), "+f"(d[O+57]), "+f"(d[O+58]), "+f"(d[O+59]), "+f"(d[O+60]), "+f"(d[O+61]), "+f"(d[O+62]), "+f"(d[O+63])
   : "r"(a0), "r"(a1), "r"(a2), "r"(a3), "l"(db), "n"(TB));
  else if constexpr (ACC == 0) asm volatile("wgmma.mma_async.sync.aligned.m64n128k16.f32.bf16.bf16 {%0,%1,%2,%3,%4,%5,%6,%7,%8,%9,%10,%11,%12,%13,%14,%15,%16,%17,%18,%19,%20,%21,%22,%23,%24,%25,%26,%27,%28,%29,%30,%31,%32,%33,%34,%35,%36,%37,%38,%39,%40,%41,%42,%43,%44,%45,%46,%47,%48,%49,%50,%51,%52,%53,%54,%55,%56,%57,%58,%59,%60,%61,%62,%63}, {%64,%65,%66,%67}, %68, 0, 1, 1, %69;"
   : "=f"(d[O+0]), "=f"(d[O+1]), "=f"(d[O+2]), "=f"(d[O+3]), "=f"(d[O+4]), "=f"(d[O+5]), "=f"(d[O+6]), "=f"(d[O+7]), "=f"(d[O+8]), "=f"(d[O+9]), "=f"(d[O+10]), "=f"(d[O+11]), "=f"(d[O+12]), "=f"(d[O+13]), "=f"(d[O+14]), "=f"(d[O+15]), "=f"(d[O+16]), "=f"(d[O+17]), "=f"(d[O+18]), "=f"(d[O+19]), "=f"(d[O+20]), "=f"(d[O+21]), "=f"(d[O+22]), "=f"(d[O+23]), "=f"(d[O+24]), "=f"(d[O+25]), "=f"(d[O+26]), "=f"(d[O+27]), "=f"(d[O+28]), "=f"(d[O+29]), "=f"(d[O+30]), "=f"(d[O+31]), "=f"(d[O+32]), "=f"(d[O+33]), "=f"(d[O+34]), "=f"(d[O+35]), "=f"(d[O+36]), "=f"(d[O+37]), "=f"(d[O+38]), "=f"(d[O+39]), "=f"(d[O+40]), "=f"(d[O+41]), "=f"(d[O+42]), "=f"(d[O+43]), "=f"(d[O+44]), "=f"(d[O+45]), "=f"(d[O+46]), "=f"(d[O+47]), "=f"(d[O+48]), "=f"(d[O+49]), "=f"(d[O+50]), "=f"(d[O+51]), "=f"(d[O+52]), "=f"(d[O+53]), "=f"(d[O+54]), "=f"(d[O+55]), "=f"(d[O+56]), "=f"(d[O+57]), "=f"(d[O+58]), "=f"(d[O+59]), "=f"(d[O+60]), "=f"(d[O+61]), "=f"(d[O+62]), "=f"(d[O+63])
   : "r"(a0), "r"(a1), "r"(a2), "r"(a3), "l"(db), "n"(TB));
  else asm volatile("{\n.reg .pred p;\nsetp.ne.b32 p, %70, 0;\nwgmma.mma_async.sync.aligned.m64n128k16.f32.bf16.bf16 {%0,%1,%2,%3,%4,%5,%6,%7,%8,%9,%10,%11,%12,%13,%14,%15,%16,%17,%18,%19,%20,%21,%22,%23,%24,%25,%26,%27,%28,%29,%30,%31,%32,%33,%34,%35,%36,%37,%38,%39,%40,%41,%42,%43,%44,%45,%46,%47,%48,%49,%50,%51,%52,%53,%54,%55,%56,%57,%58,%59,%60,%61,%62,%63}, {%64,%65,%66,%67}, %68, p, 1, 1, %69;\n}"
   : "+f"(d[O+0]), "+f"(d[O+1]), "+f"(d[O+2]), "+f"(d[O+3]), "+f"(d[O+4]), "+f"(d[O+5]), "+f"(d[O+6]), "+f"(d[O+7]), "+f"(d[O+8]), "+f"(d[O+9]), "+f"(d[O+10]), "+f"(d[O+11]), "+f"(d[O+12]), "+f"(d[O+13]), "+f"(d[O+14]), "+f"(d[O+15]), "+f"(d[O+16]), "+f"(d[O+17]), "+f"(d[O+18]), "+f"(d[O+19]), "+f"(d[O+20]), "+f"(d[O+21]), "+f"(d[O+22]), "+f"(d[O+23]), "+f"(d[O+24]), "+f"(d[O+25]), "+f"(d[O+26]), "+f"(d[O+27]), "+f"(d[O+28]), "+f"(d[O+29]), "+f"(d[O+30]), "+f"(d[O+31]), "+f"(d[O+32]), "+f"(d[O+33]), "+f"(d[O+34]), "+f"(d[O+35]), "+f"(d[O+36]), "+f"(d[O+37]), "+f"(d[O+38]), "+f"(d[O+39]), "+f"(d[O+40]), "+f"(d[O+41]), "+f"(d[O+42]), "+f"(d[O+43]), "+f"(d[O+44]), "+f"(d[O+45]), "+f"(d[O+46]), "+f"(d[O+47]), "+f"(d[O+48]), "+f"(d[O+49]), "+f"(d[O+50]), "+f"(d[O+51]), "+f"(d[O+52]), "+f"(d[O+53]), "+f"(d[O+54]), "+f"(d[O+55]), "+f"(d[O+56]), "+f"(d[O+57]), "+f"(d[O+58]), "+f"(d[O+59]), "+f"(d[O+60]), "+f"(d[O+61]), "+f"(d[O+62]), "+f"(d[O+63])
   : "r"(a0), "r"(a1), "r"(a2), "r"(a3), "l"(db), "n"(TB), "r"(sd));
}

#define NEARLY 0
#define XAHEAD 3
#define WAFTER 3
#define WPACE 50
#define GATE_AT 0
#define TPACE 40
#define PFMODE 0
#define MAPMODE 0
template <int V> struct IC { static constexpr int value = V; };
struct Maps { CUtensorMap ft, g32, x, u32, g64, u64, e, xs, ts, t, d192, d32; };

constexpr int NCTA = 130;
constexpr int U = 16384;
constexpr int TB = 36864;
constexpr int NR = 4;
constexpr int OFF_RING = 8 * U, OFF_Z = 9 * U, OFF_XB = 12 * U, OFF_T = 13 * U;
constexpr int OFF_BAR = 14 * U;
constexpr int SMEM_BYTES = OFF_BAR + 512;
constexpr int B_FX = 0, B_FA = 8, B_FT = 12, B_Z = 16, B_W = 20, B_HX = 21, B_TL = 22, B_HP = 23;
constexpr int B_EA = 26, B_ET = 30, B_RDY = 34;
constexpr int B_T = 35, B_XS = 36, NBAR = 37;
__host__ __device__ constexpr int rslot(int n) { return n % NR; }
__host__ __device__ constexpr int rpar(int n) { return (n / NR) & 1; }

__global__ void __cluster_dims__(2, 1, 1) __launch_bounds__(512, 1)
fused_kernel(const __grid_constant__ Maps maps, const __nv_bfloat16* __restrict__ x, const __nv_bfloat16* __restrict__ w_r,
             const __nv_bfloat16* __restrict__ w_i, const __nv_bfloat16* __restrict__ gate_w, const __nv_bfloat16* __restrict__ Wg,
             const __nv_bfloat16* __restrict__ Wu, __nv_bfloat16* __restrict__ out) {
  extern __shared__ __align__(1024) uint8_t smem[];
  const uint32_t sb = smem_u32(smem);
  const uint32_t bars = sb + OFF_BAR;
  const int tid = threadIdx.x, lane = tid & 31;
  const int warp = __shfl_sync(0xffffffffu, tid >> 5, 0);
  const bool helper = blockIdx.x >= 128;
  const int cl = (blockIdx.x >> 1) & 63, rank = blockIdx.x & 1;
  const int q4 = cl & 3, rb = cl >> 2;
  const int j = 2 * q4 + rank;
  const int f_full = 448 * q4 + (rank ? 256 : 0);
  const int f_half = 448 * q4 + (rank ? 224 : 192);
  const int kg = 2 * j + (rb >> 3), tn = rb & 7;

  if (tid == 64) { PROF_EV(0); PROF_CK(40); }
  auto ring_part = [&](int p, int n, int slot) {
    const uint32_t fb = bars + 8 * (B_FA + slot), dst = sb + OFF_RING + slot * U;
    const bool table = n == 9 || n == 10 || n >= 34;
    const int q = n == 8 ? 0 : n - 10;
    if (p == 0) {
      mbar_expect_tx(fb, U);
      if (n < 8) tma2d(dst, &maps.ft, fb, 64 * n, 64 * j);
      else if (table) tma4d(dst, &maps.e, fb, 0, 0, 0, 2 * rb + (n >= 34 ? n - 34 : n - 9));
      else tma2d(dst, &maps.g64, fb, f_full + 64 * (q >> 3), 64 * (q & 7));
    } else if (p == 1) {
      if (n < 8) { tma2d(dst + 8192, &maps.g32, fb, f_half, 64 * n); tma2d(dst + 12288, &maps.u32, fb, f_half, 64 * n); }
      else if (!table) tma2d(dst + 8192, &maps.u64, fb, f_full + 64 * (q >> 3), 64 * (q & 7));
    }
  };
  auto x_load = [&](int q) {
    mbar_expect_tx(bars + 8 * (B_FX + q), U);
    tma3d(sb + q * U, &maps.x, bars + 8 * (B_FX + q), 64 * q, 0, 2 * rb);
  };
  if (warp < 8) {
    if (!helper) {
      const int r8 = tid >> 3, c8 = tid & 7, r4 = tid >> 2, c4 = tid & 3;
      const uint32_t sw8 = r8 * 128 + ((c8 ^ (r8 & 7)) << 4), sw4 = r4 * 64 + ((c4 ^ ((r4 >> 1) & 3)) << 4);
      const __nv_bfloat16* px = x + (size_t)(2 * rb + 32 * r8) * 512 + 8 * c8;
      const uint16_t* pf = g_FT.v + (64 * j + r8) * 512 + 8 * c8;
      const size_t om = (size_t)r4 * 1792 + f_half + 8 * c4;
#pragma unroll
      for (int kb = 0; kb < NEARLY; kb++) {
        const uint32_t dst = sb + OFF_RING + rslot(kb) * U;
#pragma unroll
        for (int i = 0; i < 4; i++) cp16(sb + kb * U + i * 4096 + sw8, px + (i & 1) * 32 * 32 * 512 + (i >> 1) * 512 + 64 * kb);
        cp16(dst + sw8, pf + 64 * kb); cp16(dst + 4096 + sw8, pf + 32 * 512 + 64 * kb);
        cp16(dst + 8192 + sw4, Wg + om + kb * 64 * 1792); cp16(dst + 12288 + sw4, Wu + om + kb * 64 * 1792);
        asm volatile("cp.async.commit_group;" ::: "memory");
      }
    }
  } else if (warp >= 12 && lane == 0) {
    asm volatile("prefetch.tensormap [%0];" ::"l"((const char*)&maps + (warp - 12) * 128) : "memory");
    if (warp == 15) {
#pragma unroll
      for (int i = B_FT; i < NBAR; i++) mbar_init(bars + 8 * i, i < B_EA ? 1 : i < B_T ? 2 : i == B_T ? 4 : 8);
#pragma unroll
      for (int i = 0; i < 4; i++) mbar_expect_tx(bars + 8 * (B_Z + i), U);
      asm volatile("fence.mbarrier_init.release.cluster;" ::: "memory");
    } else if (warp == 14) {
#pragma unroll
      for (int i = 0; i < B_FT; i++) mbar_init(bars + 8 * i, 1);
#pragma unroll
      for (int i = 0; i < NEARLY; i++) mbar_arrive(bars + 8 * (B_FA + rslot(i)));
    } else if (warp == 13) {
#pragma unroll
      for (int i = 4; i < 12; i++) asm volatile("prefetch.tensormap [%0];" ::"l"((const char*)&maps + i * 128) : "memory");
    }
    asm volatile("fence.proxy.async.shared::cta;" ::: "memory");
  }
  if (warp >= 8) {
    __syncwarp();
    asm volatile("bar.arrive 0, 512;" ::: "memory");
    asm volatile("bar.sync 3, 256;" ::: "memory");
  }
  asm volatile("barrier.cluster.arrive.relaxed.aligned;" ::: "memory");
  if (tid == 64) PROF_EV(38);

  if (warp >= 12) {
    asm volatile("setmaxnreg.dec.sync.aligned.u32 24;");
    if (lane == 0 && (!helper || warp == 15)) {
      if (warp < 14) {
        int slot = rslot(NEARLY), par = 1;
#pragma unroll 1
        for (int n = NEARLY; n < 36; n++) {
          if (n >= NEARLY + XAHEAD && n < NR) mbar_wait(bars + 8 * (B_FX + n - XAHEAD), 0);
          mbar_wait(bars + 8 * (B_EA + slot), par);
          ring_part(warp - 12, n, slot);
          if (++slot == NR) { slot = 0; par ^= 1; }
        }
      } else if (warp == 15) {
        const unsigned ep1 = ld_x1(&g_epoch[blockIdx.x * 8]) + 1;
        mbar_expect_tx(bars + 8 * B_W, 8192);
        bulk_load(sb + OFF_T, g_DT.v, 8192, bars + 8 * B_W);
        flag_acquire(&g_cntX[helper ? 0 : 32 * j], ep1 * 16u);
        PROF_EV(22);
        mbar_expect_tx(bars + 8 * B_HX, U);
        bulk_load(sb + OFF_XB, g_X + (size_t)(helper ? 128 : kg * 8 + tn) * 8192, U, bars + 8 * B_HX);
        if (!helper) {
          flag_acquire(&g_cntT[32 * j], ep1 * 16u);
          PROF_EV(23);
          mbar_expect_tx(bars + 8 * B_TL, U);
          tma3d(sb + OFF_T, &maps.t, bars + 8 * B_TL, 64 * j, 0, 2 * rb);
#pragma unroll 1
          for (int i = 0; i < 3; i++) { hint_wait(&g_cntP[32 * (rb * 8 + j) + i], ep1 * 8u); mbar_arrive(bars + 8 * (B_HP + i)); }
        }
      } else {
#pragma unroll 1
        for (int q = NEARLY; q < 8; q++) { if (q >= NEARLY + XAHEAD) mbar_wait(bars + 8 * (B_FX + q - XAHEAD), 0); x_load(q); }
        PROF_EV(31);
        mbar_wait(bars + 8 * B_XS, 0);
#pragma unroll
        for (int h2 = 0; h2 < 2; h2++) {
          const int s0 = 2 * rb + h2, sg = (s0 & ~6) | ((s0 & 2) << 1) | ((s0 & 4) >> 1);
          asm volatile("cp.async.bulk.tensor.4d.global.shared::cta.bulk_group [%0, {%2, %3, %4, %5}], [%1];" ::"l"(&maps.xs), "r"(sb + OFF_XB + h2 * 8192),
                       "r"(0), "r"(sg), "r"(0), "r"(16 * j) : "memory");
          if (j == 0) {
#pragma unroll
            for (int c = 0; c < 2; c++)
              asm volatile("cp.async.bulk.global.shared::cta.bulk_group [%0], [%1], 256;" ::"l"(g_X + 128 * 8192 + c * 4096 + sg * 128),
                           "r"(sb + OFF_T + 8192 + h2 * 512 + c * 256) : "memory");
          }
        }
        bulk_done_release(&g_cntX[32 * j]);
        PROF_EV(20);
#pragma unroll 1
        for (int t = 0; t < 8; t++) {
          const int i = t < 3 ? t + 1 : t < 6 ? t - 2 : 0;
          const int col = 64 * (2 * ((q4 + i) & 3) + ((t < 3 || t == 6) ? 1 - rank : rank));
          const uint32_t fb = bars + 8 * (B_FT + (t & 3)), dst = sb + (t & 3) * TB;
          mbar_wait(bars + 8 * (B_ET + (t & 3)), t >> 2);
          mbar_expect_tx(fb, TB);
          tma2d(dst, &maps.d192, fb, col, f_full);
          tma2d(dst + 24576, &maps.d32, fb, col, f_half);
          tma2d(dst + 28672, &maps.ft, fb, col, 64 * j);
        }
      }
    }
  } else if (warp >= 8) {
    asm volatile("setmaxnreg.dec.sync.aligned.u32 104;");
    const int t = tid - 256, w = warp - 8;
    const uint32_t ep = ld_x1(&g_epoch[blockIdx.x * 8]);
    const uint32_t tag = (ep + 1) & 1;
    auto gate_rows = [&] {
      uint4 xv[8], gv[2];
#pragma unroll
      for (int i = 0; i < 4; i++) {
        const int r = 16 * j + 4 * w + i;
        const uint4* p = (const uint4*)(x + (size_t)(2 * rb + (r >> 6) + 32 * (r & 63)) * 512) + lane;
        xv[2 * i] = __ldg(p); xv[2 * i + 1] = __ldg(p + 32);
      }
      gv[0] = __ldg((const uint4*)gate_w + lane); gv[1] = __ldg((const uint4*)gate_w + lane + 32);
      {
        float z[4];
#pragma unroll
        for (int i = 0; i < 4; i++) {
          float a = 0.f;
#pragma unroll
          for (int hh = 0; hh < 2; hh++) {
            const uint4 u = xv[2 * i + hh], v = gv[hh];
            a = fmaf(bf_lo(u.x), bf_lo(v.x), a); a = fmaf(bf_hi(u.x), bf_hi(v.x), a);
            a = fmaf(bf_lo(u.y), bf_lo(v.y), a); a = fmaf(bf_hi(u.y), bf_hi(v.y), a);
            a = fmaf(bf_lo(u.z), bf_lo(v.z), a); a = fmaf(bf_hi(u.z), bf_hi(v.z), a);
            a = fmaf(bf_lo(u.w), bf_lo(v.w), a); a = fmaf(bf_hi(u.w), bf_hi(v.w), a);
          }
#pragma unroll
          for (int o = 16; o; o >>= 1) a += __shfl_xor_sync(0xffffffffu, a, o);
          z[i] = a;
        }
        if (lane < 4) {
          const float zz = lane == 0 ? z[0] : lane == 1 ? z[1] : lane == 2 ? z[2] : z[3];
          asm volatile("st.relaxed.gpu.global.f32 [%0], %1;" ::"l"(g_gate + rb * 128 + 16 * j + 4 * w + lane), "f"(tagf(1.0f / (1.0f + __expf(-zz)), tag)) : "memory");
        }
        if (t == 0) PROF_EV(18);
      }
      if (w == 0) {
        const int c = lane >> 4, jj = 16 * blockIdx.x + (lane & 15), jm = (2048 - jj) & 2047;
        const unsigned short* pr = (const unsigned short*)w_r + 256 * c;
        const unsigned short* pi = (const unsigned short*)w_i + 256 * c;
        const float wr = 0.25f * (bf_lo(__ldg(pr + jj * 257)) + bf_lo(__ldg(pr + jm * 257)));
        const float wi = 0.25f * (bf_lo(__ldg(pi + jj * 257)) - bf_lo(__ldg(pi + jm * 257)));
        st_u2(g_Wh + c * 2048 + jj, c ? pack_bf16(-wi, wr) : pack_bf16(wr, wi), tag);
        __syncwarp();
        if (lane == 0) hint_add(&g_cntW[0]);
      }
    };
    {
      const int g = lane >> 2, q = lane & 3;
      uint32_t wf[32];
      if (!helper) {
        const int o = (8 * tn + 2 * w + 64 * q) * 257 + 16 * kg + g;
        const unsigned short* pr = (const unsigned short*)w_r + o;
        const unsigned short* pi = (const unsigned short*)w_i + o;
#pragma unroll
        for (int i = 0; i < 32; i++) {
          const int d = (i >> 4) * 8 + (i & 1) * 257 + ((i >> 1) & 7) * 256 * 257;
          wf[i] = (uint32_t)__ldg(pr + d) | ((uint32_t)__ldg(pi + d) << 16);
        }
#pragma unroll
        for (int i = 0; i < 32; i++) asm volatile("" : "+r"(wf[i])::"memory");
        if (t == 0) PROF_EV(11);
        gate_rows();
      } else {
        hint_wait(&g_cntW[0], (ep + 1) * 128u);
        const uint32_t t0 = (uint32_t)clock();
#pragma unroll 1
        for (;;) {
          uint32_t bad = 0;
#pragma unroll
          for (int i = 0; i < 32; i++) {
            const float2 v = ld_x2((const float2*)g_Wh + (i >> 4) * 2048 + 16 * w + g + 8 * (i & 1) + 64 * q + ((i >> 1) & 7) * 256);
            wf[i] = __float_as_uint(v.x); bad |= __float_as_uint(v.y) ^ tag;
          }
          if (!__any_sync(0xffffffffu, bad & 1)) break;
          spin_guard(t0);
        }
        if (t == 0) PROF_EV(11);
      }
      mbar_wait(bars + 8 * B_W, 0);
      mbar_wait(bars + 8 * B_HX, 0);
      if (t == 0) PROF_EV(12);
      const uint32_t dd = (sb & 0x3FFFF) >> 4;
      const uint64_t dF = d128((dd + (OFF_T >> 4)) | (512u << 16)), dI = d128((dd + (OFF_T >> 4)) | (1u << 16)), dA = d128((dd + (OFF_XB >> 4)) | (512u << 16));
      float az[32];
      const int zero = blockIdx.x >> 16;
      uint32_t pf[32];
#pragma unroll
      for (int mt = 0; mt < 2; mt++) {
        wg_fence();
        if (mt == 0) mma_ss64<0, 3, 0>(az, dA, dF);
        else mma_ss64<0, 3, 2>(az, dA + 512, dF, zero);
#pragma unroll
        for (int k = 1; k < 4; k++) mma_ss64<0, 3, 1>(az, dA + (mt * 512 + k * 128), dF + k * 128);
        wg_commit();
        wg_wait<0>();
        fence_regs<0, 32>(az);
#pragma unroll
        for (int i = 0; i < 16; i++) {
          const float wr = bf_lo(wf[16 * mt + i]), wi = bf_hi(wf[16 * mt + i]);
          pf[16 * mt + i] = pack_pin(fmaf(az[2 * i], wr, -az[2 * i + 1] * wi), fmaf(az[2 * i], wi, az[2 * i + 1] * wr));
        }
      }
      if (t == 0) PROF_EV(16);
#pragma unroll
      for (int mt = 0; mt < 2; mt++) {
        wg_fence();
        mma_rs64<0, 0, 2>(az, pf[16 * mt], pf[16 * mt + 1], pf[16 * mt + 2], pf[16 * mt + 3], dI, mt ? (int)helper : zero);
#pragma unroll
        for (int k = 1; k < 4; k++) mma_rs64<0, 0, 1>(az, pf[16 * mt + 4 * k], pf[16 * mt + 4 * k + 1], pf[16 * mt + 4 * k + 2], pf[16 * mt + 4 * k + 3], dI + k * 2);
        wg_commit();
        wg_wait<0>();
        fence_regs<0, 32>(az);
        if (!helper) {
          const int m = lane >> 3, r = lane & 7;
          const int sl = 2 * (m >> 1) + ((r >> 1) & 1) + 4 * (r >> 2);
          const uint32_t a0 = sb + OFF_XB + (2 * w + (m & 1)) * 2048 + sl * 64 + (((mt * 2 + (r & 1)) ^ (sl >> 1)) << 4);
#pragma unroll
          for (int i = 0; i < 4; i++)
            stsm4t(a0 + i * 512, pack_bf16(az[8 * i], az[8 * i + 1]), pack_bf16(az[8 * i + 2], az[8 * i + 3]), pack_bf16(az[8 * i + 4], az[8 * i + 5]),
                   pack_bf16(az[8 * i + 6], az[8 * i + 7]));
        }
      }
      if (helper) {
#pragma unroll
        for (int i = 0; i < 16; i++) {
          const int n = i >> 1, s0 = 8 * (n >> 1) + 2 * (n & 1) + (q & 1) + 4 * (q >> 1);
          if ((n & 1) == (int)(blockIdx.x & 1)) st_u2(g_Ts + s0 * 64 + 16 * w + g + 8 * (i & 1), pack_bf16(az[2 * i], az[2 * i + 1]), tag);
        }
        __syncwarp();
        if (lane == 0) hint_add(&g_cntH[0]);
        if (t == 0) { g_epoch[blockIdx.x * 8] = ep + 1; PROF_EV(13); }
      } else {
        asm volatile("fence.proxy.async.shared::cta;" ::: "memory");
        asm volatile("bar.sync 1, 128;" ::: "memory");
        if (t == 0) {
          PROF_EV(17);
          asm volatile("cp.async.bulk.tensor.3d.global.shared::cta.bulk_group [%0, {%2, %3, %4}], [%1];" ::"l"(&maps.ts), "r"(sb + OFF_XB),
                       "r"(32 * kg), "r"(0), "r"(8 * tn) : "memory");
          bulk_done_release(&g_cntT[32 * j]);
          PROF_EV(13);
        }
        __syncwarp();
        if (j == 0) {
          hint_wait(&g_cntH[0], (ep + 1) * 8u);
          const uint32_t t0 = (uint32_t)clock();
          float2 v;
          do { v = ld_x2((const float2*)g_Ts + 2 * rb * 64 + t); spin_guard(t0); } while (__any_sync(0xffffffffu, (__float_as_uint(v.y) ^ tag) & 1));
          mbar_wait(bars + 8 * B_TL, 0);
          const uint32_t u = __float_as_uint(v.x);
          *(uint16_t*)(smem + OFF_T + t * 128 + ((t & 7) << 4)) = (uint16_t)u;
          *(uint16_t*)(smem + OFF_T + t * 128 + (((t & 7) ^ 1) << 4)) = (uint16_t)(u >> 16);
          asm volatile("fence.proxy.async.shared::cta;" ::: "memory");
          __syncwarp();
          if (lane == 0) mbar_arrive(bars + 8 * B_T);
        }
      }
    }
  } else {
    asm volatile("setmaxnreg.inc.sync.aligned.u32 192;");
    if (!helper) {
      const int wg = warp >> 2, w = warp & 3, g = lane >> 2, q = lane & 3;
      const bool elect = (tid & 127) == 0;
      const uint32_t ep = ld_x1(&g_epoch[blockIdx.x * 8]);
      float c1[64], cA[64], c2[64], ci[64], ct[64];
      const int zero = blockIdx.x >> 16;
      uint32_t h[56], yf[16];
      const uint32_t d0 = (sb & 0x3FFFF) >> 4;
      const uint32_t dK = d0 | (1u << 16), dN = d0 | (512u << 16), dM = d0 | (256u << 16);
      const uint32_t dX = dK + wg * 512;
      constexpr uint32_t RING = OFF_RING >> 4;
      auto waitA = [&](int n) { mbar_wait(bars + 8 * (B_FA + rslot(n)), rpar(n)); };
      auto freeA = [&](int n) { if (elect) mbar_arrive(bars + 8 * (B_EA + rslot(n))); };
      auto nop = [](int) {};

#pragma unroll
      for (int kb = 0; kb < 8; kb++) {
        if (kb < NEARLY) {
          if (NEARLY - 1 - kb == 3) asm volatile("cp.async.wait_group 3;" ::: "memory");
          else if (NEARLY - 1 - kb == 2) asm volatile("cp.async.wait_group 2;" ::: "memory");
          else if (NEARLY - 1 - kb == 1) asm volatile("cp.async.wait_group 1;" ::: "memory");
          else asm volatile("cp.async.wait_group 0;" ::: "memory");
          asm volatile("fence.proxy.async.shared::cta;" ::: "memory");
          if (kb == 0) asm volatile("bar.sync 0, 512;" ::: "memory");
          else asm volatile("bar.sync 2, 256;" ::: "memory");
        } else {
          if (kb == 0) asm volatile("bar.sync 0, 512;" ::: "memory");
          mbar_wait(bars + 8 * (B_FX + kb), 0); waitA(kb);
        }
        wg_fence();
        const uint64_t dx = d128(dX + kb * 1024), df = d128(dK + RING + rslot(kb) * 1024), dm = d64(dM + RING + 512 + rslot(kb) * 1024);
        if (kb == 0) { mma_ss64<0, 0, 0>(c1, df, dx); mma_ss64<32, 1, 0>(c1, dx, dm); }
        else { mma_ss64<0, 0, 1>(c1, df, dx); mma_ss64<32, 1, 1>(c1, dx, dm); wg_commit(); wg_wait<1>(); freeA(kb - 1); }
#pragma unroll
        for (int k = 1; k < 4; k++) {
          mma_ss64<0, 0, 1>(c1, df + k * 2, dx + k * 2);
          mma_ss64<32, 1, 1>(c1, dx + k * 2, dm + k * 64);
        }
        wg_commit();
        if (kb == 0 && tid == 0) PROF_EV(1);
      }
      auto ffn_step = [&](auto first, float (&acc)[64], int n, int kb, auto done, auto work) {
        waitA(n);
        wg_fence();
        const uint64_t dx = d128(dX + kb * 1024), db = d128(dN + RING + rslot(n) * 1024);
        mma_ss128<0, 1, decltype(first)::value>(acc, dx, db, zero);
        wg_commit();
        wg_wait<1>();
        done();
#pragma unroll
        for (int k = 1; k < 4; k++) { mma_ss128<0, 1, 1>(acc, dx + k * 2, db + k * 128); work(k - 1); }
        wg_commit();
        work(3);
      };
      const uint32_t tag = (ep + 1) & 1;
      float hm[16];
      ffn_step(IC<0>(), c2, 8, 0, [&] { freeA(7); fence_regs<0, 64>(c1); }, [&](int i) {
#pragma unroll
        for (int e = 4 * i; e < 4 * i + 4; e++) { yf[e] = pack_pin(c1[2 * e], c1[2 * e + 1]); hm[e] = fmaxf(c1[32 + e], 0.f) * c1[48 + e]; }
      });
      fence_regs<0, 16>(hm);
      if (tid == 0) PROF_EV(2);
      {
        waitA(9); waitA(10);
        const uint64_t de = d128(dN + RING + (wg ? rslot(10) : rslot(9)) * 1024);
        wg_fence();
        mma_rs128<0, 1, 0>(cA, yf[0], yf[1], yf[2], yf[3], de);
        wg_commit();
        wg_wait<1>();
        freeA(8);
#pragma unroll
        for (int k = 1; k < 4; k++) mma_rs128<0, 1, 1>(cA, yf[4 * k], yf[4 * k + 1], yf[4 * k + 2], yf[4 * k + 3], de + k * 128);
        wg_commit();
      }
      {
        const int s0 = 2 * rb + wg, kr = 2 * ((s0 & 1) | ((s0 & 4) >> 1));
        const int m = lane >> 3, r = lane & 7;
        const uint32_t a0 = sb + OFF_XB + wg * 8192 + (((w >> 1) * 8 + (m >> 1)) * 2 + (w & 1)) * 256 + (m & 1) * 128 + ((r ^ (kr + (m & 1))) << 4);
        ffn_step(IC<1>(), c2, 11, 1, [&] { freeA(9); freeA(10); fence_regs<0, 64>(cA); }, [&](int i) {
          stsm4t(a0 + i * 1024, pack_bf16(cA[8 * i] - cA[34 + 8 * i], cA[8 * i + 1] - cA[35 + 8 * i]),
                 pack_bf16(cA[32 + 8 * i] + cA[8 * i + 2], cA[33 + 8 * i] + cA[8 * i + 3]),
                 pack_bf16(cA[8 * i + 4] - cA[38 + 8 * i], cA[8 * i + 5] - cA[39 + 8 * i]),
                 pack_bf16(cA[36 + 8 * i] + cA[8 * i + 6], cA[37 + 8 * i] + cA[8 * i + 7]));
        });
        if (j == 0 && w == 0 && g == 0) {
#pragma unroll
          for (int n = 0; n < 8; n++)
#pragma unroll
            for (int ce = 0; ce < 4; ce++)
              *(uint32_t*)(smem + OFF_T + 8192 + wg * 512 + ce * 128 + ((n ^ (kr + (ce & 1))) << 4) + 4 * q) =
                  pack_bf16(cA[(ce & 1) * 32 + 4 * n + (ce & 2)], cA[(ce & 1) * 32 + 4 * n + (ce & 2) + 1]);
        }
        asm volatile("fence.proxy.async.shared::cta;" ::: "memory");
        __syncwarp();
        if (lane == 0) mbar_arrive(bars + 8 * B_XS);
        if (tid == 0) PROF_EV(3);
      }
      const float* gp = g_gate + rb * 128 + wg * 64 + w * 16 + g;
      uint32_t gb0 = ld_x1(gp), gb1 = ld_x1(gp + 8);
#pragma unroll
      for (int kb = 2; kb < 7; kb++) ffn_step(IC<1>(), c2, 10 + kb, kb, [&] { freeA(9 + kb); }, nop);
      {
        const uint32_t t0 = (uint32_t)clock();
        while (__any_sync(0xffffffffu, ((gb0 ^ tag) | (gb1 ^ tag)) & 1)) { gb0 = ld_x1(gp); gb1 = ld_x1(gp + 8); spin_guard(t0); }
      }
      const float g0 = __uint_as_float(gb0 & ~1u), g1 = __uint_as_float(gb1 & ~1u);
      const float o0 = 1.0f - g0, o1 = 1.0f - g1;
      uint32_t hp[8];
      ffn_step(IC<1>(), c2, 17, 7, [&] { freeA(16); }, [&](int i) {
        hp[2 * i] = pack_pin(hm[4 * i] * o0, hm[4 * i + 1] * o0); hp[2 * i + 1] = pack_pin(hm[4 * i + 2] * o1, hm[4 * i + 3] * o1);
      });
      auto glu = [&](float (&acc)[64], int ho, int i0, int i1) {
#pragma unroll
        for (int i = i0; i < i1; i++) {
          const float o = (i & 1) ? o1 : o0;
          h[ho + i] = pack_pin(fmaxf(acc[2 * i], 0.f) * acc[32 + 2 * i] * o, fmaxf(acc[2 * i + 1], 0.f) * acc[33 + 2 * i] * o);
        }
      };
      ffn_step(IC<2>(), cA, 18, 0, [&] { freeA(17); fence_regs<0, 64>(c2); }, [&](int i) { glu(c2, 0, 2 * i, 2 * i + 2); });
      if (tid == 0) PROF_EV(4);
      ffn_step(IC<1>(), cA, 19, 1, [&] { freeA(18); }, [&](int i) { glu(c2, 0, 8 + 2 * i, 10 + 2 * i); });
#pragma unroll
      for (int kb = 2; kb < 8; kb++) ffn_step(IC<1>(), cA, 18 + kb, kb, [&] { freeA(17 + kb); }, nop);
      ffn_step(IC<2>(), c2, 26, 0, [&] { freeA(25); fence_regs<0, 64>(cA); }, [&](int i) { glu(cA, 16, 2 * i, 2 * i + 2); });
      if (tid == 0) PROF_EV(5);
      ffn_step(IC<1>(), c2, 27, 1, [&] { freeA(26); }, [&](int i) { glu(cA, 16, 8 + 2 * i, 10 + 2 * i); });
#pragma unroll
      for (int kb = 2; kb < 8; kb++)
        ffn_step(IC<1>(), c2, 26 + kb, kb, [&] {
          if (kb < 7) freeA(25 + kb);
          if (kb >= 3 && (kb & 1) && elect) mbar_arrive(bars + 8 * (B_ET + ((kb - 3) >> 1)));
        }, nop);
      wg_wait<0>();
      if (elect) mbar_arrive(bars + 8 * (B_ET + 3));
      fence_regs<0, 64>(c2);
      glu(c2, 32, 0, 16);
#pragma unroll
      for (int i = 0; i < 8; i++) h[48 + i] = hp[i] ^ zero;
      if (wg) waitA(35); else waitA(34);
      if (tid == 0) PROF_EV(6);
      mbar_wait(bars + 8 * (j == 0 ? B_T : B_TL), 0);
      if (tid == 0) PROF_EV(7);
      wg_fence();
      {
        const uint64_t dt = d128(dN + (OFF_T >> 4) + wg * 512), de = d128(dK + RING + (wg ? rslot(35) : rslot(34)) * 1024);
        mma_ss64<0, 1, 0>(ci, de, dt);
        mma_ss64<32, 1, 0>(ci, de + 512, dt);
#pragma unroll
        for (int k = 1; k < 4; k++) {
          mma_ss64<0, 1, 1>(ci, de + k * 2, dt + k * 128);
          mma_ss64<32, 1, 1>(ci, de + (512 + k * 2), dt + k * 128);
        }
      }
      wg_commit();

      auto head = [&](auto off, int t) {
        constexpr int O = decltype(off)::value;
        mbar_wait(bars + 8 * (B_FT + (t & 3)), t >> 2);
        const uint64_t db = d128(dN + (t & 3) * (TB >> 4));
        wg_fence();
        mma_rs64<O, 1, 0>(ct, h[0], h[1], h[2], h[3], db);
#pragma unroll
        for (int k = 1; k < 6; k++) mma_rs64<O, 1, 1>(ct, h[4 * k], h[4 * k + 1], h[4 * k + 2], h[4 * k + 3], db + k * 128);
        wg_commit();
        wg_wait<1>();
      };
      auto rest = [&](auto off, int t) {
        constexpr int O = decltype(off)::value;
        const uint64_t db = d128(dN + (t & 3) * (TB >> 4));
        wg_fence();
#pragma unroll
        for (int k = 6; k < 14; k++) mma_rs64<O, 1, 1>(ct, h[4 * k], h[4 * k + 1], h[4 * k + 2], h[4 * k + 3], db + k * 128);
#pragma unroll
        for (int k = 0; k < 4; k++) mma_rs64<O, 1, 1>(ct, yf[4 * k], yf[4 * k + 1], yf[4 * k + 2], yf[4 * k + 3], db + (14 + k) * 128);
        wg_commit();
      };
      auto freeT = [&](int t) { if (elect) mbar_arrive(bars + 8 * (B_ET + t)); };
      const uint32_t peerZ = mapa(sb + OFF_Z + tid * 16, rank ^ 1), peerB = mapa(bars + 8 * B_Z, rank ^ 1);
      auto send_peer = [&](auto off, int z) {
        constexpr int O = decltype(off)::value;
        fence_regs<O, 32>(ct);
#pragma unroll
        for (int i = 0; i < 4; i++)
          asm volatile("st.async.weak.shared::cluster.mbarrier::complete_tx::bytes.v4.b32 [%0], {%1,%2,%3,%4}, [%5];" ::"r"(peerZ + z * U + i * 4096),
                       "r"(pack_bf16(ct[O + 8 * i], ct[O + 8 * i + 1])), "r"(pack_bf16(ct[O + 8 * i + 2], ct[O + 8 * i + 3])),
                       "r"(pack_bf16(ct[O + 8 * i + 4], ct[O + 8 * i + 5])), "r"(pack_bf16(ct[O + 8 * i + 6], ct[O + 8 * i + 7])), "r"(peerB + 8 * z) : "memory");
      };
      auto send_grid = [&](auto off, int z) {
        constexpr int O = decltype(off)::value;
        fence_regs<O, 32>(ct);
        mbar_wait(bars + 8 * (B_Z + z), 0);
        uint4* dst = g_part + (size_t)((rb * 8 + 2 * ((q4 + z + 1) & 3) + rank) * 3 + z) * 1024 + tid;
#pragma unroll
        for (int i = 0; i < 4; i++) {
          const uint4 p = *(const uint4*)(smem + OFF_Z + z * U + i * 4096 + tid * 16);
          st_x4(dst + i * 256, (pack_bf16(ct[O + 8 * i] + bf_lo(p.x), ct[O + 8 * i + 1] + bf_hi(p.x)) & ~1u) | tag,
                pack_bf16(ct[O + 8 * i + 2] + bf_lo(p.y), ct[O + 8 * i + 3] + bf_hi(p.y)),
                pack_bf16(ct[O + 8 * i + 4] + bf_lo(p.z), ct[O + 8 * i + 5] + bf_hi(p.z)),
                pack_bf16(ct[O + 8 * i + 6] + bf_lo(p.w), ct[O + 8 * i + 7] + bf_hi(p.w)));
        }
        __syncwarp();
        if (lane == 0) hint_add(&g_cntP[32 * (rb * 8 + 2 * ((q4 + z + 1) & 3) + rank) + z]);
      };
      asm volatile("barrier.cluster.wait.aligned;" ::: "memory");
      head(IC<0>(), 0);
      if (elect) asm volatile("mbarrier.arrive.shared::cluster.b64 _, [%0];" ::"r"(mapa(bars + 8 * B_RDY, rank ^ 1)) : "memory");
      fence_regs<0, 64>(ci);
#pragma unroll
      for (int i = 0; i < 16; i++) {
        const float gg = ((i & 1) ? g1 : g0) * (2.0f / (2048.0f * 512.0f));
        if (i & 2) yf[i] = pack_pin((ci[2 * i] - ci[28 + 2 * i]) * gg, (ci[2 * i + 1] - ci[29 + 2 * i]) * gg);
        else yf[i] = pack_pin((ci[2 * i] + ci[36 + 2 * i]) * gg, (ci[2 * i + 1] + ci[37 + 2 * i]) * gg);
      }
      rest(IC<0>(), 0);
      if (tid == 0) PROF_EV(8);
      head(IC<32>(), 1); freeT(0); mbar_wait(bars + 8 * B_RDY, 0); send_peer(IC<0>(), 0); rest(IC<32>(), 1);
      head(IC<0>(), 2); freeT(1); send_peer(IC<32>(), 1); rest(IC<0>(), 2);
      head(IC<32>(), 3); freeT(2); send_peer(IC<0>(), 2); rest(IC<32>(), 3);
      head(IC<0>(), 4); freeT(3); send_grid(IC<32>(), 0); rest(IC<0>(), 4);
      head(IC<32>(), 5); send_grid(IC<0>(), 1); rest(IC<32>(), 5);
      head(IC<0>(), 6); send_grid(IC<32>(), 2); rest(IC<0>(), 6);
      head(IC<32>(), 7); send_peer(IC<0>(), 3);
      {
        const uint4* src = g_part + (size_t)(rb * 8 + j) * 3 * 1024 + tid;
        uint4 pv[12];
        mbar_wait(bars + 8 * (B_HP + 1), 0);
#pragma unroll
        for (int i = 0; i < 8; i++) pv[i] = ld_x4(src + i * 256);
        rest(IC<32>(), 7);
        if (tid == 0) PROF_EV(9);
        mbar_wait(bars + 8 * (B_HP + 2), 0);
        if (tid == 0) PROF_EV(24);
#pragma unroll
        for (int i = 8; i < 12; i++) pv[i] = ld_x4(src + i * 256);
        const uint32_t t0 = (uint32_t)clock();
        for (;;) {
          uint32_t bad = 0;
#pragma unroll
          for (int i = 0; i < 12; i++) bad |= pv[i].x ^ tag;
          if (!__any_sync(0xffffffffu, bad & 1)) break;
#pragma unroll
          for (int i = 0; i < 12; i++) pv[i] = ld_x4(src + i * 256);
          spin_guard(t0);
        }
        if (tid == 0) PROF_EV(14);
        float sum[32];
#pragma unroll
        for (int i = 0; i < 4; i++) {
          const uint32_t a[4] = {pv[i].x & ~1u, pv[i].y, pv[i].z, pv[i].w}, b[4] = {pv[4 + i].x & ~1u, pv[4 + i].y, pv[4 + i].z, pv[4 + i].w},
                         c[4] = {pv[8 + i].x & ~1u, pv[8 + i].y, pv[8 + i].z, pv[8 + i].w};
#pragma unroll
          for (int e = 0; e < 4; e++) {
            sum[8 * i + 2 * e] = bf_lo(a[e]) + bf_lo(b[e]) + bf_lo(c[e]);
            sum[8 * i + 2 * e + 1] = bf_hi(a[e]) + bf_hi(b[e]) + bf_hi(c[e]);
          }
        }
        mbar_wait(bars + 8 * (B_Z + 3), 0);
#pragma unroll
        for (int i = 0; i < 4; i++) {
          const uint4 p = *(const uint4*)(smem + OFF_Z + 3 * U + i * 4096 + tid * 16);
          const uint32_t a[4] = {p.x, p.y, p.z, p.w};
#pragma unroll
          for (int e = 0; e < 4; e++) { sum[8 * i + 2 * e] += bf_lo(a[e]); sum[8 * i + 2 * e + 1] += bf_hi(a[e]); }
        }
        wg_wait<0>();
        fence_regs<32, 32>(ct);
#pragma unroll
        for (int i = 0; i < 32; i++) sum[i] += ct[32 + i];
        const uint32_t stg = sb + OFF_T + warp * 2048;
        const int mr = (lane & 7) + ((lane >> 3) & 1) * 8, mc = lane >> 4;
#pragma unroll
        for (int i = 0; i < 4; i++) {
          const uint32_t a = stg + mr * 128 + (((2 * i + mc) ^ (mr & 7)) << 4);
          asm volatile("stmatrix.sync.aligned.m8n8.x4.shared.b16 [%0], {%1,%2,%3,%4};" ::"r"(a), "r"(pack_bf16(sum[8 * i], sum[8 * i + 1])),
                       "r"(pack_bf16(sum[8 * i + 2], sum[8 * i + 3])), "r"(pack_bf16(sum[8 * i + 4], sum[8 * i + 5])),
                       "r"(pack_bf16(sum[8 * i + 6], sum[8 * i + 7])) : "memory");
        }
        __syncwarp();
#pragma unroll
        for (int i = 0; i < 4; i++) {
          const int r = 4 * i + (lane >> 3), c = lane & 7;
          const uint4 v = *(const uint4*)(smem + OFF_T + warp * 2048 + r * 128 + ((c ^ (r & 7)) << 4));
          *(uint4*)(out + (size_t)(2 * rb + wg + 32 * (16 * w + r)) * 512 + 64 * j + 8 * c) = v;
        }
      }
      if (tid == 0) { g_epoch[blockIdx.x * 8] = ep + 1; PROF_EV(15); PROF_CK(41); }
    }
  }
}

typedef CUresult (*EncodeFn)(CUtensorMap*, CUtensorMapDataType, cuuint32_t, void*, const cuuint64_t*, const cuuint64_t*, const cuuint32_t*,
                             const cuuint32_t*, CUtensorMapInterleave, CUtensorMapSwizzle, CUtensorMapL2promotion, CUtensorMapFloatOOBfill);

static void encode(EncodeFn f, CUtensorMap* m, const void* base, int rank, const cuuint64_t* dims, const cuuint64_t* strides, const cuuint32_t* box,
                   CUtensorMapSwizzle sw) {
  cuuint32_t es[5] = {1, 1, 1, 1, 1};
  f(m, CU_TENSOR_MAP_DATA_TYPE_BFLOAT16, rank, (void*)base, dims, strides, box, es, CU_TENSOR_MAP_INTERLEAVE_NONE, sw,
    CU_TENSOR_MAP_L2_PROMOTION_L2_128B, CU_TENSOR_MAP_FLOAT_OOB_FILL_NONE);
}

extern "C" void kernel_launch(void* const* d_in, const int* in_sizes, int n_in, void* d_out, int out_size) {
  (void)in_sizes; (void)n_in; (void)out_size;
  const __nv_bfloat16* x = (const __nv_bfloat16*)d_in[0];
  const __nv_bfloat16* w_r = (const __nv_bfloat16*)d_in[1];
  const __nv_bfloat16* w_i = (const __nv_bfloat16*)d_in[2];
  const __nv_bfloat16* Wg = (const __nv_bfloat16*)d_in[4];
  const __nv_bfloat16* Wu = (const __nv_bfloat16*)d_in[5];
  const __nv_bfloat16* Wd = (const __nv_bfloat16*)d_in[6];
  const __nv_bfloat16* gw = (const __nv_bfloat16*)d_in[7];

  void* fp = nullptr; cudaDriverEntryPointQueryResult qr;
  cudaGetDriverEntryPoint("cuTensorMapEncodeTiled", &fp, cudaEnableDefault, &qr);
  EncodeFn enc = (EncodeFn)fp;
  void *pFT, *pET, *pX, *pT;
  cudaGetSymbolAddress(&pX, g_X); cudaGetSymbolAddress(&pT, g_T);
  cudaGetSymbolAddress(&pFT, g_FT); cudaGetSymbolAddress(&pET, g_ET);

  Maps mp;
  const CUtensorMapSwizzle S128 = CU_TENSOR_MAP_SWIZZLE_128B, S64 = CU_TENSOR_MAP_SWIZZLE_64B;
  { cuuint64_t d[3] = {512, 64, 32}, s[2] = {32768, 1024}; cuuint32_t b[3] = {64, 64, 2}; encode(enc, &mp.x, x, 3, d, s, b, S128); }
  { cuuint64_t d[2] = {512, 512}, s[1] = {1024}; cuuint32_t b[2] = {64, 64}; encode(enc, &mp.ft, pFT, 2, d, s, b, S128); }
  { cuuint64_t d[4] = {128, 32, 2, 129}, s[3] = {256, 8192, 16384}; cuuint32_t b[4] = {128, 1, 2, 16}; encode(enc, &mp.xs, pX, 4, d, s, b, CU_TENSOR_MAP_SWIZZLE_NONE); }
  { cuuint64_t d[3] = {512, 32, 64}, s[2] = {65536, 1024}; cuuint32_t b[3] = {32, 32, 8}; encode(enc, &mp.ts, pT, 3, d, s, b, S64); }
  { cuuint64_t d[3] = {512, 64, 32}, s[2] = {1024, 65536}; cuuint32_t b[3] = {64, 64, 2}; encode(enc, &mp.t, pT, 3, d, s, b, S128); }
  { cuuint64_t d[4] = {64, 64, 2, 32}, s[3] = {8192, 128, 256}; cuuint32_t b[4] = {64, 64, 2, 1}; encode(enc, &mp.e, pET, 4, d, s, b, S128); }
  { cuuint64_t d[2] = {1792, 512}, s[1] = {3584}; cuuint32_t b[2] = {64, 64}, b2[2] = {32, 64};
    encode(enc, &mp.g64, Wg, 2, d, s, b, S128); encode(enc, &mp.u64, Wu, 2, d, s, b, S128);
    encode(enc, &mp.g32, Wg, 2, d, s, b2, S64); encode(enc, &mp.u32, Wu, 2, d, s, b2, S64); }
  { cuuint64_t d[2] = {512, 1792}, s[1] = {1024}; cuuint32_t b[2] = {64, 192}, b2[2] = {64, 32};
    encode(enc, &mp.d192, Wd, 2, d, s, b, S128); encode(enc, &mp.d32, Wd, 2, d, s, b2, S128); }

  cudaFuncSetAttribute(fused_kernel, cudaFuncAttributeMaxDynamicSharedMemorySize, SMEM_BYTES);
  fused_kernel<<<NCTA, 512, SMEM_BYTES>>>(mp, x, w_r, w_i, gw, Wg, Wu, (__nv_bfloat16*)d_out);
}
```

```cpp
#include <cuda_runtime.h>
#include <cuda_bf16.h>
#include <cuda.h>
#include <stdint.h>

namespace tbl {
constexpr double PI = 3.14159265358979323846264338327950288;
constexpr double sin_s(double x) { double t = x, s = x; for (int n = 1; n < 12; n++) { t *= -x * x / ((2 * n) * (2 * n + 1)); s += t; } return s; }
constexpr double cos_s(double x) { double t = 1, s = 1; for (int n = 1; n < 12; n++) { t *= -x * x / ((2 * n - 1) * (2 * n)); s += t; } return s; }
constexpr double cos2048(int m) {
  m &= 2047; if (m > 1024) m = 2048 - m;
  bool neg = false; if (m > 512) { m = 1024 - m; neg = true; }
  double v = (m <= 256) ? cos_s(2 * PI * m / 2048) : sin_s(2 * PI * (512 - m) / 2048);
  return neg ? -v : v;
}
constexpr uint16_t to_bf16(double v) {
  if (v == 0) return 0;
  uint16_t s = 0; if (v < 0) { s = 0x8000; v = -v; }
  int e = 0; while (v >= 2) { v /= 2; e++; } while (v < 1) { v *= 2; e--; }
  double m = (v - 1) * 128; int mi = (int)m; double fr = m - mi;
  if (fr > 0.5 || (fr == 0.5 && (mi & 1))) mi++;
  if (mi == 128) { mi = 0; e++; }
  return (uint16_t)(s | ((e + 127) << 7) | mi);
}
struct CosT { uint16_t v[2048]; constexpr CosT() : v() { for (int i = 0; i < 2048; i++) v[i] = to_bf16(cos2048(i)); } };
struct alignas(1024) FT {
  uint16_t v[512 * 512];
  constexpr FT() : v() {
    CosT c;
    for (int r = 0; r < 512; r++) {
      int k = (r >> 4) * 8 + (r & 7), e = (r >> 3) & 1;
      int mul = 4 * k, add = e ? 512 : 0;
      if (k == 0 && e == 1) { mul = 1024; add = 0; }
      for (int d = 0; d < 512; d++) v[r * 512 + d] = c.v[(d * mul + add) & 2047];
    }
  }
};
struct alignas(1024) ET {
  uint16_t v[2048 * 128];
  constexpr ET() : v() {
    CosT c;
    for (int s = 0; s < 2048; s++)
      for (int j = 0; j < 64; j++) { v[s * 128 + j] = c.v[(s * j) & 2047]; v[s * 128 + 64 + j] = c.v[(s * j + 512) & 2047]; }
  }
};
struct alignas(1024) DT {
  uint16_t v[64 * 64];
  constexpr DT() : v() {
    CosT c;
    for (int r = 0; r < 64; r++)
      for (int n = 0; n < 64; n++) {
        const int sg = r >> 1, s0 = (sg & ~6) | ((sg & 2) << 1) | ((sg & 4) >> 1), e = r & 1, f = n & 1;
        const int m = 64 * s0 * (n >> 1) + (e == f ? 0 : e ? -512 : 512);
        v[r * 64 + (((n >> 3) ^ (r & 7)) << 3) + (n & 7)] = c.v[m & 2047];
      }
  }
};
}

__device__ constexpr tbl::FT g_FT = tbl::FT();
__device__ constexpr tbl::ET g_ET = tbl::ET();
__device__ constexpr tbl::DT g_DT = tbl::DT();

__device__ __align__(1024) uint16_t g_X[129 * 8192];
__device__ __align__(1024) uint16_t g_T[32 * 64 * 512];
__device__ __align__(1024) uint2 g_Ts[32 * 64];
__device__ __align__(1024) uint4 g_part[128 * 3 * 1024];
__device__ __align__(16) float g_gate[16 * 128];
__device__ __align__(16) uint2 g_Wh[2 * 2048];
__device__ unsigned g_epoch[132 * 8];
__device__ unsigned g_cntX[8 * 32], g_cntT[8 * 32], g_cntP[128 * 32], g_cntW[32], g_cntH[32];
#define PROF_EV(i) do {} while (0)
#define PROF_CK(i) do {} while (0)

__device__ __forceinline__ uint32_t smem_u32(const void* p) { return (uint32_t)__cvta_generic_to_shared(p); }
__device__ __forceinline__ void mbar_init(uint32_t bar, uint32_t cnt) { asm volatile("mbarrier.init.shared::cta.b64 [%0], %1;" ::"r"(bar), "r"(cnt)); }
__device__ __forceinline__ void mbar_expect_tx(uint32_t bar, uint32_t bytes) { asm volatile("mbarrier.arrive.expect_tx.shared::cta.b64 _, [%0], %1;" ::"r"(bar), "r"(bytes) : "memory"); }
__device__ __forceinline__ void mbar_arrive(uint32_t bar) { asm volatile("mbarrier.arrive.shared::cta.b64 _, [%0];" ::"r"(bar) : "memory"); }
__device__ __forceinline__ void mbar_wait(uint32_t bar, uint32_t parity) {
  asm volatile(
      "{\n.reg .pred p;\n.reg .u32 n;\nmov.u32 n, 0;\n"
      "W_LOOP:\nmbarrier.try_wait.parity.shared::cta.b64 p, [%0], %1;\n@p bra W_DONE;\n"
      "add.u32 n, n, 1;\nsetp.lt.u32 p, n, 0x40000;\n@p bra W_LOOP;\ntrap;\nW_DONE:\n}" ::"r"(bar), "r"(parity) : "memory");
}
__device__ __forceinline__ void bulk_load(uint32_t dst, const void* src, uint32_t bytes, uint32_t bar) {
  asm volatile("cp.async.bulk.shared::cluster.global.mbarrier::complete_tx::bytes [%0], [%1], %2, [%3];" ::"r"(dst), "l"(src), "r"(bytes), "r"(bar) : "memory");
}
__device__ __forceinline__ void cp16(uint32_t dst, const void* src) { asm volatile("cp.async.cg.shared.global [%0], [%1], 16;" ::"r"(dst), "l"(src) : "memory"); }
__device__ __forceinline__ void spin_guard(uint32_t t0) { if ((uint32_t)clock() - t0 > (1u << 30)) __trap(); }
__device__ __forceinline__ float tagf(float v, uint32_t tag) { return __uint_as_float((__float_as_uint(v) & ~1u) | tag); }
__device__ __forceinline__ float untag(float v) { return __uint_as_float(__float_as_uint(v) & ~1u); }
__device__ __forceinline__ void st_x2(float2* p, float a, float b) { asm volatile("st.relaxed.gpu.global.v2.f32 [%0], {%1,%2};" ::"l"(p), "f"(a), "f"(b) : "memory"); }
__device__ __forceinline__ float2 ld_x2(const float2* p) { float2 v; asm volatile("ld.relaxed.gpu.global.v2.f32 {%0,%1}, [%2];" : "=f"(v.x), "=f"(v.y) : "l"(p) : "memory"); return v; }
__device__ __forceinline__ void st_u2(uint2* p, uint32_t a, uint32_t b) { asm volatile("st.relaxed.gpu.global.v2.u32 [%0], {%1,%2};" ::"l"(p), "r"(a), "r"(b) : "memory"); }
__device__ __forceinline__ void prefetch2d(const CUtensorMap* m, int c0, int c1) { asm volatile("cp.async.bulk.prefetch.tensor.2d.L2.global [%0, {%1, %2}];" ::"l"(m), "r"(c0), "r"(c1) : "memory"); }
__device__ __forceinline__ void prefetch1d(const void* p, uint32_t bytes) { asm volatile("cp.async.bulk.prefetch.L2.global [%0], %1;" ::"l"(p), "r"(bytes) : "memory"); }
__device__ __forceinline__ uint32_t ld_x1(const void* p) { uint32_t v; asm volatile("ld.relaxed.gpu.global.u32 %0, [%1];" : "=r"(v) : "l"(p) : "memory"); return v; }
__device__ __forceinline__ uint4 ld_x4(const void* p) { uint4 v; asm volatile("ld.relaxed.gpu.global.v4.u32 {%0,%1,%2,%3}, [%4];" : "=r"(v.x), "=r"(v.y), "=r"(v.z), "=r"(v.w) : "l"(p) : "memory"); return v; }
__device__ __forceinline__ void st_x4(void* p, uint32_t a, uint32_t b, uint32_t c, uint32_t d) { asm volatile("st.relaxed.gpu.global.v4.u32 [%0], {%1,%2,%3,%4};" ::"l"(p), "r"(a), "r"(b), "r"(c), "r"(d) : "memory"); }
__device__ __forceinline__ uint32_t mapa(uint32_t a, uint32_t cta) { uint32_t r; asm volatile("mapa.shared::cluster.u32 %0, %1, %2;" : "=r"(r) : "r"(a), "r"(cta)); return r; }
__device__ __forceinline__ void stsm4t(uint32_t a, uint32_t r0, uint32_t r1, uint32_t r2, uint32_t r3) {
  asm volatile("stmatrix.sync.aligned.m8n8.x4.trans.shared.b16 [%0], {%1,%2,%3,%4};" ::"r"(a), "r"(r0), "r"(r1), "r"(r2), "r"(r3) : "memory");
}
__device__ __forceinline__ void hint_add(unsigned* p) { asm volatile("red.relaxed.gpu.global.add.u32 [%0], 1;" ::"l"(p) : "memory"); }
__device__ __forceinline__ void hint_wait(const unsigned* p, unsigned target) {
  const uint32_t t0 = (uint32_t)clock();
  while ((int)(ld_x1(p) - target) < 0) spin_guard(t0);
}
__device__ __forceinline__ void bulk_done_signal(unsigned* p) {
  asm volatile("cp.async.bulk.commit_group;\ncp.async.bulk.wait_group 0;\nfence.proxy.async.global;" ::: "memory");
  hint_add(p);
}
__device__ __forceinline__ void flag_wait(const unsigned* p, unsigned target) {
  hint_wait(p, target);
  asm volatile("fence.proxy.async.global;" ::: "memory");
}
__device__ __forceinline__ void tma2d(uint32_t dst, const CUtensorMap* m, uint32_t bar, int c0, int c1) {
  asm volatile("cp.async.bulk.tensor.2d.shared::cluster.global.mbarrier::complete_tx::bytes [%0], [%1, {%3, %4}], [%2];" ::"r"(dst), "l"(m), "r"(bar), "r"(c0), "r"(c1) : "memory");
}
__device__ __forceinline__ void tma3d(uint32_t dst, const CUtensorMap* m, uint32_t bar, int c0, int c1, int c2) {
  asm volatile("cp.async.bulk.tensor.3d.shared::cluster.global.mbarrier::complete_tx::bytes [%0], [%1, {%3, %4, %5}], [%2];" ::"r"(dst), "l"(m), "r"(bar), "r"(c0), "r"(c1), "r"(c2) : "memory");
}
__device__ __forceinline__ void tma4d(uint32_t dst, const CUtensorMap* m, uint32_t bar, int c0, int c1, int c2, int c3) {
  asm volatile("cp.async.bulk.tensor.4d.shared::cluster.global.mbarrier::complete_tx::bytes [%0], [%1, {%3, %4, %5, %6}], [%2];" ::"r"(dst), "l"(m), "r"(bar), "r"(c0), "r"(c1), "r"(c2), "r"(c3) : "memory");
}
__device__ __forceinline__ void wg_fence() { asm volatile("wgmma.fence.sync.aligned;" ::: "memory"); }
__device__ __forceinline__ void wg_commit() { asm volatile("wgmma.commit_group.sync.aligned;" ::: "memory"); }
template <int N> __device__ __forceinline__ void wg_wait() { asm volatile("wgmma.wait_group.sync.aligned %0;" ::"n"(N) : "memory"); }
template <int O, int N, int NN> __device__ __forceinline__ void fence_regs(float (&d)[NN]) {
#pragma unroll
  for (int i = 0; i < N; i++) asm volatile("" : "+f"(d[O + i])::"memory");
}
__device__ __forceinline__ uint32_t pack_bf16(float lo, float hi) {
  uint32_t r; asm("cvt.rn.bf16x2.f32 %0, %1, %2;" : "=r"(r) : "f"(hi), "f"(lo)); return r;
}
__device__ __forceinline__ uint32_t pack_pin(float lo, float hi) {
  uint32_t r; asm volatile("cvt.rn.bf16x2.f32 %0, %1, %2;" : "=r"(r) : "f"(hi), "f"(lo) : "memory"); return r;
}
__device__ __forceinline__ float bf_lo(uint32_t u) { return __uint_as_float(u << 16); }
__device__ __forceinline__ float bf_hi(uint32_t u) { return __uint_as_float(u & 0xffff0000u); }

__device__ __forceinline__ uint64_t d128(uint32_t lo) { uint64_t d; asm("mov.b64 %0, {%1, 0x40000040};" : "=l"(d) : "r"(lo)); return d; }
__device__ __forceinline__ uint64_t d64(uint32_t lo) { uint64_t d; asm("mov.b64 %0, {%1, 0x80000020};" : "=l"(d) : "r"(lo)); return d; }
template<int O,int TB,int ACC,int NN> __device__ __forceinline__ void mma_ss64(float (&d)[NN], uint64_t da, uint64_t db, int sd = 0){
  if constexpr (ACC == 1) asm volatile("wgmma.mma_async.sync.aligned.m64n64k16.f32.bf16.bf16 {%0,%1,%2,%3,%4,%5,%6,%7,%8,%9,%10,%11,%12,%13,%14,%15,%16,%17,%18,%19,%20,%21,%22,%23,%24,%25,%26,%27,%28,%29,%30,%31}, %32, %33, 1, 1, 1, %35, %34;"
   : "+f"(d[O+0]), "+f"(d[O+1]), "+f"(d[O+2]), "+f"(d[O+3]), "+f"(d[O+4]), "+f"(d[O+5]), "+f"(d[O+6]), "+f"(d[O+7]), "+f"(d[O+8]), "+f"(d[O+9]), "+f"(d[O+10]), "+f"(d[O+11]), "+f"(d[O+12]), "+f"(d[O+13]), "+f"(d[O+14]), "+f"(d[O+15]), "+f"(d[O+16]), "+f"(d[O+17]), "+f"(d[O+18]), "+f"(d[O+19]), "+f"(d[O+20]), "+f"(d[O+21]), "+f"(d[O+22]), "+f"(d[O+23]), "+f"(d[O+24]), "+f"(d[O+25]), "+f"(d[O+26]), "+f"(d[O+27]), "+f"(d[O+28]), "+f"(d[O+29]), "+f"(d[O+30]), "+f"(d[O+31])
   : "l"(da), "l"(db), "n"(TB & 1), "n"(TB >> 1));
  else if constexpr (ACC == 0) asm volatile("wgmma.mma_async.sync.aligned.m64n64k16.f32.bf16.bf16 {%0,%1,%2,%3,%4,%5,%6,%7,%8,%9,%10,%11,%12,%13,%14,%15,%16,%17,%18,%19,%20,%21,%22,%23,%24,%25,%26,%27,%28,%29,%30,%31}, %32, %33, 0, 1, 1, %35, %34;"
   : "=f"(d[O+0]), "=f"(d[O+1]), "=f"(d[O+2]), "=f"(d[O+3]), "=f"(d[O+4]), "=f"(d[O+5]), "=f"(d[O+6]), "=f"(d[O+7]), "=f"(d[O+8]), "=f"(d[O+9]), "=f"(d[O+10]), "=f"(d[O+11]), "=f"(d[O+12]), "=f"(d[O+13]), "=f"(d[O+14]), "=f"(d[O+15]), "=f"(d[O+16]), "=f"(d[O+17]), "=f"(d[O+18]), "=f"(d[O+19]), "=f"(d[O+20]), "=f"(d[O+21]), "=f"(d[O+22]), "=f"(d[O+23]), "=f"(d[O+24]), "=f"(d[O+25]), "=f"(d[O+26]), "=f"(d[O+27]), "=f"(d[O+28]), "=f"(d[O+29]), "=f"(d[O+30]), "=f"(d[O+31])
   : "l"(da), "l"(db), "n"(TB & 1), "n"(TB >> 1));
  else asm volatile("{\n.reg .pred p;\nsetp.ne.b32 p, %36, 0;\nwgmma.mma_async.sync.aligned.m64n64k16.f32.bf16.bf16 {%0,%1,%2,%3,%4,%5,%6,%7,%8,%9,%10,%11,%12,%13,%14,%15,%16,%17,%18,%19,%20,%21,%22,%23,%24,%25,%26,%27,%28,%29,%30,%31}, %32, %33, p, 1, 1, %35, %34;\n}"
   : "+f"(d[O+0]), "+f"(d[O+1]), "+f"(d[O+2]), "+f"(d[O+3]), "+f"(d[O+4]), "+f"(d[O+5]), "+f"(d[O+6]), "+f"(d[O+7]), "+f"(d[O+8]), "+f"(d[O+9]), "+f"(d[O+10]), "+f"(d[O+11]), "+f"(d[O+12]), "+f"(d[O+13]), "+f"(d[O+14]), "+f"(d[O+15]), "+f"(d[O+16]), "+f"(d[O+17]), "+f"(d[O+18]), "+f"(d[O+19]), "+f"(d[O+20]), "+f"(d[O+21]), "+f"(d[O+22]), "+f"(d[O+23]), "+f"(d[O+24]), "+f"(d[O+25]), "+f"(d[O+26]), "+f"(d[O+27]), "+f"(d[O+28]), "+f"(d[O+29]), "+f"(d[O+30]), "+f"(d[O+31])
   : "l"(da), "l"(db), "n"(TB & 1), "n"(TB >> 1), "r"(sd));
}
template<int O,int TB,int ACC,int NN> __device__ __forceinline__ void mma_rs64(float (&d)[NN], uint32_t a0, uint32_t a1, uint32_t a2, uint32_t a3, uint64_t db, int sd = 0){
  if constexpr (ACC == 1) asm volatile("wgmma.mma_async.sync.aligned.m64n64k16.f32.bf16.bf16 {%0,%1,%2,%3,%4,%5,%6,%7,%8,%9,%10,%11,%12,%13,%14,%15,%16,%17,%18,%19,%20,%21,%22,%23,%24,%25,%26,%27,%28,%29,%30,%31}, {%32,%33,%34,%35}, %36, 1, 1, 1, %37;"
   : "+f"(d[O+0]), "+f"(d[O+1]), "+f"(d[O+2]), "+f"(d[O+3]), "+f"(d[O+4]), "+f"(d[O+5]), "+f"(d[O+6]), "+f"(d[O+7]), "+f"(d[O+8]), "+f"(d[O+9]), "+f"(d[O+10]), "+f"(d[O+11]), "+f"(d[O+12]), "+f"(d[O+13]), "+f"(d[O+14]), "+f"(d[O+15]), "+f"(d[O+16]), "+f"(d[O+17]), "+f"(d[O+18]), "+f"(d[O+19]), "+f"(d[O+20]), "+f"(d[O+21]), "+f"(d[O+22]), "+f"(d[O+23]), "+f"(d[O+24]), "+f"(d[O+25]), "+f"(d[O+26]), "+f"(d[O+27]), "+f"(d[O+28]), "+f"(d[O+29]), "+f"(d[O+30]), "+f"(d[O+31])
   : "r"(a0), "r"(a1), "r"(a2), "r"(a3), "l"(db), "n"(TB));
  else if constexpr (ACC == 0) asm volatile("wgmma.mma_async.sync.aligned.m64n64k16.f32.bf16.bf16 {%0,%1,%2,%3,%4,%5,%6,%7,%8,%9,%10,%11,%12,%13,%14,%15,%16,%17,%18,%19,%20,%21,%22,%23,%24,%25,%26,%27,%28,%29,%30,%31}, {%32,%33,%34,%35}, %36, 0, 1, 1, %37;"
   : "=f"(d[O+0]), "=f"(d[O+1]), "=f"(d[O+2]), "=f"(d[O+3]), "=f"(d[O+4]), "=f"(d[O+5]), "=f"(d[O+6]), "=f"(d[O+7]), "=f"(d[O+8]), "=f"(d[O+9]), "=f"(d[O+10]), "=f"(d[O+11]), "=f"(d[O+12]), "=f"(d[O+13]), "=f"(d[O+14]), "=f"(d[O+15]), "=f"(d[O+16]), "=f"(d[O+17]), "=f"(d[O+18]), "=f"(d[O+19]), "=f"(d[O+20]), "=f"(d[O+21]), "=f"(d[O+22]), "=f"(d[O+23]), "=f"(d[O+24]), "=f"(d[O+25]), "=f"(d[O+26]), "=f"(d[O+27]), "=f"(d[O+28]), "=f"(d[O+29]), "=f"(d[O+30]), "=f"(d[O+31])
   : "r"(a0), "r"(a1), "r"(a2), "r"(a3), "l"(db), "n"(TB));
  else asm volatile("{\n.reg .pred p;\nsetp.ne.b32 p, %38, 0;\nwgmma.mma_async.sync.aligned.m64n64k16.f32.bf16.bf16 {%0,%1,%2,%3,%4,%5,%6,%7,%8,%9,%10,%11,%12,%13,%14,%15,%16,%17,%18,%19,%20,%21,%22,%23,%24,%25,%26,%27,%28,%29,%30,%31}, {%32,%33,%34,%35}, %36, p, 1, 1, %37;\n}"
   : "+f"(d[O+0]), "+f"(d[O+1]), "+f"(d[O+2]), "+f"(d[O+3]), "+f"(d[O+4]), "+f"(d[O+5]), "+f"(d[O+6]), "+f"(d[O+7]), "+f"(d[O+8]), "+f"(d[O+9]), "+f"(d[O+10]), "+f"(d[O+11]), "+f"(d[O+12]), "+f"(d[O+13]), "+f"(d[O+14]), "+f"(d[O+15]), "+f"(d[O+16]), "+f"(d[O+17]), "+f"(d[O+18]), "+f"(d[O+19]), "+f"(d[O+20]), "+f"(d[O+21]), "+f"(d[O+22]), "+f"(d[O+23]), "+f"(d[O+24]), "+f"(d[O+25]), "+f"(d[O+26]), "+f"(d[O+27]), "+f"(d[O+28]), "+f"(d[O+29]), "+f"(d[O+30]), "+f"(d[O+31])
   : "r"(a0), "r"(a1), "r"(a2), "r"(a3), "l"(db), "n"(TB), "r"(sd));
}
template<int O,int TB,int ACC,int NN> __device__ __forceinline__ void mma_ss128(float (&d)[NN], uint64_t da, uint64_t db, int sd = 0){
  if constexpr (ACC == 1) asm volatile("wgmma.mma_async.sync.aligned.m64n128k16.f32.bf16.bf16 {%0,%1,%2,%3,%4,%5,%6,%7,%8,%9,%10,%11,%12,%13,%14,%15,%16,%17,%18,%19,%20,%21,%22,%23,%24,%25,%26,%27,%28,%29,%30,%31,%32,%33,%34,%35,%36,%37,%38,%39,%40,%41,%42,%43,%44,%45,%46,%47,%48,%49,%50,%51,%52,%53,%54,%55,%56,%57,%58,%59,%60,%61,%62,%63}, %64, %65, 1, 1, 1, %67, %66;"
   : "+f"(d[O+0]), "+f"(d[O+1]), "+f"(d[O+2]), "+f"(d[O+3]), "+f"(d[O+4]), "+f"(d[O+5]), "+f"(d[O+6]), "+f"(d[O+7]), "+f"(d[O+8]), "+f"(d[O+9]), "+f"(d[O+10]), "+f"(d[O+11]), "+f"(d[O+12]), "+f"(d[O+13]), "+f"(d[O+14]), "+f"(d[O+15]), "+f"(d[O+16]), "+f"(d[O+17]), "+f"(d[O+18]), "+f"(d[O+19]), "+f"(d[O+20]), "+f"(d[O+21]), "+f"(d[O+22]), "+f"(d[O+23]), "+f"(d[O+24]), "+f"(d[O+25]), "+f"(d[O+26]), "+f"(d[O+27]), "+f"(d[O+28]), "+f"(d[O+29]), "+f"(d[O+30]), "+f"(d[O+31]), "+f"(d[O+32]), "+f"(d[O+33]), "+f"(d[O+34]), "+f"(d[O+35]), "+f"(d[O+36]), "+f"(d[O+37]), "+f"(d[O+38]), "+f"(d[O+39]), "+f"(d[O+40]), "+f"(d[O+41]), "+f"(d[O+42]), "+f"(d[O+43]), "+f"(d[O+44]), "+f"(d[O+45]), "+f"(d[O+46]), "+f"(d[O+47]), "+f"(d[O+48]), "+f"(d[O+49]), "+f"(d[O+50]), "+f"(d[O+51]), "+f"(d[O+52]), "+f"(d[O+53]), "+f"(d[O+54]), "+f"(d[O+55]), "+f"(d[O+56]), "+f"(d[O+57]), "+f"(d[O+58]), "+f"(d[O+59]), "+f"(d[O+60]), "+f"(d[O+61]), "+f"(d[O+62]), "+f"(d[O+63])
   : "l"(da), "l"(db), "n"(TB & 1), "n"(TB >> 1));
  else if constexpr (ACC == 0) asm volatile("wgmma.mma_async.sync.aligned.m64n128k16.f32.bf16.bf16 {%0,%1,%2,%3,%4,%5,%6,%7,%8,%9,%10,%11,%12,%13,%14,%15,%16,%17,%18,%19,%20,%21,%22,%23,%24,%25,%26,%27,%28,%29,%30,%31,%32,%33,%34,%35,%36,%37,%38,%39,%40,%41,%42,%43,%44,%45,%46,%47,%48,%49,%50,%51,%52,%53,%54,%55,%56,%57,%58,%59,%60,%61,%62,%63}, %64, %65, 0, 1, 1, %67, %66;"
   : "=f"(d[O+0]), "=f"(d[O+1]), "=f"(d[O+2]), "=f"(d[O+3]), "=f"(d[O+4]), "=f"(d[O+5]), "=f"(d[O+6]), "=f"(d[O+7]), "=f"(d[O+8]), "=f"(d[O+9]), "=f"(d[O+10]), "=f"(d[O+11]), "=f"(d[O+12]), "=f"(d[O+13]), "=f"(d[O+14]), "=f"(d[O+15]), "=f"(d[O+16]), "=f"(d[O+17]), "=f"(d[O+18]), "=f"(d[O+19]), "=f"(d[O+20]), "=f"(d[O+21]), "=f"(d[O+22]), "=f"(d[O+23]), "=f"(d[O+24]), "=f"(d[O+25]), "=f"(d[O+26]), "=f"(d[O+27]), "=f"(d[O+28]), "=f"(d[O+29]), "=f"(d[O+30]), "=f"(d[O+31]), "=f"(d[O+32]), "=f"(d[O+33]), "=f"(d[O+34]), "=f"(d[O+35]), "=f"(d[O+36]), "=f"(d[O+37]), "=f"(d[O+38]), "=f"(d[O+39]), "=f"(d[O+40]), "=f"(d[O+41]), "=f"(d[O+42]), "=f"(d[O+43]), "=f"(d[O+44]), "=f"(d[O+45]), "=f"(d[O+46]), "=f"(d[O+47]), "=f"(d[O+48]), "=f"(d[O+49]), "=f"(d[O+50]), "=f"(d[O+51]), "=f"(d[O+52]), "=f"(d[O+53]), "=f"(d[O+54]), "=f"(d[O+55]), "=f"(d[O+56]), "=f"(d[O+57]), "=f"(d[O+58]), "=f"(d[O+59]), "=f"(d[O+60]), "=f"(d[O+61]), "=f"(d[O+62]), "=f"(d[O+63])
   : "l"(da), "l"(db), "n"(TB & 1), "n"(TB >> 1));
  else asm volatile("{\n.reg .pred p;\nsetp.ne.b32 p, %68, 0;\nwgmma.mma_async.sync.aligned.m64n128k16.f32.bf16.bf16 {%0,%1,%2,%3,%4,%5,%6,%7,%8,%9,%10,%11,%12,%13,%14,%15,%16,%17,%18,%19,%20,%21,%22,%23,%24,%25,%26,%27,%28,%29,%30,%31,%32,%33,%34,%35,%36,%37,%38,%39,%40,%41,%42,%43,%44,%45,%46,%47,%48,%49,%50,%51,%52,%53,%54,%55,%56,%57,%58,%59,%60,%61,%62,%63}, %64, %65, p, 1, 1, %67, %66;\n}"
   : "+f"(d[O+0]), "+f"(d[O+1]), "+f"(d[O+2]), "+f"(d[O+3]), "+f"(d[O+4]), "+f"(d[O+5]), "+f"(d[O+6]), "+f"(d[O+7]), "+f"(d[O+8]), "+f"(d[O+9]), "+f"(d[O+10]), "+f"(d[O+11]), "+f"(d[O+12]), "+f"(d[O+13]), "+f"(d[O+14]), "+f"(d[O+15]), "+f"(d[O+16]), "+f"(d[O+17]), "+f"(d[O+18]), "+f"(d[O+19]), "+f"(d[O+20]), "+f"(d[O+21]), "+f"(d[O+22]), "+f"(d[O+23]), "+f"(d[O+24]), "+f"(d[O+25]), "+f"(d[O+26]), "+f"(d[O+27]), "+f"(d[O+28]), "+f"(d[O+29]), "+f"(d[O+30]), "+f"(d[O+31]), "+f"(d[O+32]), "+f"(d[O+33]), "+f"(d[O+34]), "+f"(d[O+35]), "+f"(d[O+36]), "+f"(d[O+37]), "+f"(d[O+38]), "+f"(d[O+39]), "+f"(d[O+40]), "+f"(d[O+41]), "+f"(d[O+42]), "+f"(d[O+43]), "+f"(d[O+44]), "+f"(d[O+45]), "+f"(d[O+46]), "+f"(d[O+47]), "+f"(d[O+48]), "+f"(d[O+49]), "+f"(d[O+50]), "+f"(d[O+51]), "+f"(d[O+52]), "+f"(d[O+53]), "+f"(d[O+54]), "+f"(d[O+55]), "+f"(d[O+56]), "+f"(d[O+57]), "+f"(d[O+58]), "+f"(d[O+59]), "+f"(d[O+60]), "+f"(d[O+61]), "+f"(d[O+62]), "+f"(d[O+63])
   : "l"(da), "l"(db), "n"(TB & 1), "n"(TB >> 1), "r"(sd));
}
template<int O,int TB,int ACC,int NN> __device__ __forceinline__ void mma_rs128(float (&d)[NN], uint32_t a0, uint32_t a1, uint32_t a2, uint32_t a3, uint64_t db, int sd = 0){
  if constexpr (ACC == 1) asm volatile("wgmma.mma_async.sync.aligned.m64n128k16.f32.bf16.bf16 {%0,%1,%2,%3,%4,%5,%6,%7,%8,%9,%10,%11,%12,%13,%14,%15,%16,%17,%18,%19,%20,%21,%22,%23,%24,%25,%26,%27,%28,%29,%30,%31,%32,%33,%34,%35,%36,%37,%38,%39,%40,%41,%42,%43,%44,%45,%46,%47,%48,%49,%50,%51,%52,%53,%54,%55,%56,%57,%58,%59,%60,%61,%62,%63}, {%64,%65,%66,%67}, %68, 1, 1, 1, %69;"
   : "+f"(d[O+0]), "+f"(d[O+1]), "+f"(d[O+2]), "+f"(d[O+3]), "+f"(d[O+4]), "+f"(d[O+5]), "+f"(d[O+6]), "+f"(d[O+7]), "+f"(d[O+8]), "+f"(d[O+9]), "+f"(d[O+10]), "+f"(d[O+11]), "+f"(d[O+12]), "+f"(d[O+13]), "+f"(d[O+14]), "+f"(d[O+15]), "+f"(d[O+16]), "+f"(d[O+17]), "+f"(d[O+18]), "+f"(d[O+19]), "+f"(d[O+20]), "+f"(d[O+21]), "+f"(d[O+22]), "+f"(d[O+23]), "+f"(d[O+24]), "+f"(d[O+25]), "+f"(d[O+26]), "+f"(d[O+27]), "+f"(d[O+28]), "+f"(d[O+29]), "+f"(d[O+30]), "+f"(d[O+31]), "+f"(d[O+32]), "+f"(d[O+33]), "+f"(d[O+34]), "+f"(d[O+35]), "+f"(d[O+36]), "+f"(d[O+37]), "+f"(d[O+38]), "+f"(d[O+39]), "+f"(d[O+40]), "+f"(d[O+41]), "+f"(d[O+42]), "+f"(d[O+43]), "+f"(d[O+44]), "+f"(d[O+45]), "+f"(d[O+46]), "+f"(d[O+47]), "+f"(d[O+48]), "+f"(d[O+49]), "+f"(d[O+50]), "+f"(d[O+51]), "+f"(d[O+52]), "+f"(d[O+53]), "+f"(d[O+54]), "+f"(d[O+55]), "+f"(d[O+56]), "+f"(d[O+57]), "+f"(d[O+58]), "+f"(d[O+59]), "+f"(d[O+60]), "+f"(d[O+61]), "+f"(d[O+62]), "+f"(d[O+63])
   : "r"(a0), "r"(a1), "r"(a2), "r"(a3), "l"(db), "n"(TB));
  else if constexpr (ACC == 0) asm volatile("wgmma.mma_async.sync.aligned.m64n128k16.f32.bf16.bf16 {%0,%1,%2,%3,%4,%5,%6,%7,%8,%9,%10,%11,%12,%13,%14,%15,%16,%17,%18,%19,%20,%21,%22,%23,%24,%25,%26,%27,%28,%29,%30,%31,%32,%33,%34,%35,%36,%37,%38,%39,%40,%41,%42,%43,%44,%45,%46,%47,%48,%49,%50,%51,%52,%53,%54,%55,%56,%57,%58,%59,%60,%61,%62,%63}, {%64,%65,%66,%67}, %68, 0, 1, 1, %69;"
   : "=f"(d[O+0]), "=f"(d[O+1]), "=f"(d[O+2]), "=f"(d[O+3]), "=f"(d[O+4]), "=f"(d[O+5]), "=f"(d[O+6]), "=f"(d[O+7]), "=f"(d[O+8]), "=f"(d[O+9]), "=f"(d[O+10]), "=f"(d[O+11]), "=f"(d[O+12]), "=f"(d[O+13]), "=f"(d[O+14]), "=f"(d[O+15]), "=f"(d[O+16]), "=f"(d[O+17]), "=f"(d[O+18]), "=f"(d[O+19]), "=f"(d[O+20]), "=f"(d[O+21]), "=f"(d[O+22]), "=f"(d[O+23]), "=f"(d[O+24]), "=f"(d[O+25]), "=f"(d[O+26]), "=f"(d[O+27]), "=f"(d[O+28]), "=f"(d[O+29]), "=f"(d[O+30]), "=f"(d[O+31]), "=f"(d[O+32]), "=f"(d[O+33]), "=f"(d[O+34]), "=f"(d[O+35]), "=f"(d[O+36]), "=f"(d[O+37]), "=f"(d[O+38]), "=f"(d[O+39]), "=f"(d[O+40]), "=f"(d[O+41]), "=f"(d[O+42]), "=f"(d[O+43]), "=f"(d[O+44]), "=f"(d[O+45]), "=f"(d[O+46]), "=f"(d[O+47]), "=f"(d[O+48]), "=f"(d[O+49]), "=f"(d[O+50]), "=f"(d[O+51]), "=f"(d[O+52]), "=f"(d[O+53]), "=f"(d[O+54]), "=f"(d[O+55]), "=f"(d[O+56]), "=f"(d[O+57]), "=f"(d[O+58]), "=f"(d[O+59]), "=f"(d[O+60]), "=f"(d[O+61]), "=f"(d[O+62]), "=f"(d[O+63])
   : "r"(a0), "r"(a1), "r"(a2), "r"(a3), "l"(db), "n"(TB));
  else asm volatile("{\n.reg .pred p;\nsetp.ne.b32 p, %70, 0;\nwgmma.mma_async.sync.aligned.m64n128k16.f32.bf16.bf16 {%0,%1,%2,%3,%4,%5,%6,%7,%8,%9,%10,%11,%12,%13,%14,%15,%16,%17,%18,%19,%20,%21,%22,%23,%24,%25,%26,%27,%28,%29,%30,%31,%32,%33,%34,%35,%36,%37,%38,%39,%40,%41,%42,%43,%44,%45,%46,%47,%48,%49,%50,%51,%52,%53,%54,%55,%56,%57,%58,%59,%60,%61,%62,%63}, {%64,%65,%66,%67}, %68, p, 1, 1, %69;\n}"
   : "+f"(d[O+0]), "+f"(d[O+1]), "+f"(d[O+2]), "+f"(d[O+3]), "+f"(d[O+4]), "+f"(d[O+5]), "+f"(d[O+6]), "+f"(d[O+7]), "+f"(d[O+8]), "+f"(d[O+9]), "+f"(d[O+10]), "+f"(d[O+11]), "+f"(d[O+12]), "+f"(d[O+13]), "+f"(d[O+14]), "+f"(d[O+15]), "+f"(d[O+16]), "+f"(d[O+17]), "+f"(d[O+18]), "+f"(d[O+19]), "+f"(d[O+20]), "+f"(d[O+21]), "+f"(d[O+22]), "+f"(d[O+23]), "+f"(d[O+24]), "+f"(d[O+25]), "+f"(d[O+26]), "+f"(d[O+27]), "+f"(d[O+28]), "+f"(d[O+29]), "+f"(d[O+30]), "+f"(d[O+31]), "+f"(d[O+32]), "+f"(d[O+33]), "+f"(d[O+34]), "+f"(d[O+35]), "+f"(d[O+36]), "+f"(d[O+37]), "+f"(d[O+38]), "+f"(d[O+39]), "+f"(d[O+40]), "+f"(d[O+41]), "+f"(d[O+42]), "+f"(d[O+43]), "+f"(d[O+44]), "+f"(d[O+45]), "+f"(d[O+46]), "+f"(d[O+47]), "+f"(d[O+48]), "+f"(d[O+49]), "+f"(d[O+50]), "+f"(d[O+51]), "+f"(d[O+52]), "+f"(d[O+53]), "+f"(d[O+54]), "+f"(d[O+55]), "+f"(d[O+56]), "+f"(d[O+57]), "+f"(d[O+58]), "+f"(d[O+59]), "+f"(d[O+60]), "+f"(d[O+61]), "+f"(d[O+62]), "+f"(d[O+63])
   : "r"(a0), "r"(a1), "r"(a2), "r"(a3), "l"(db), "n"(TB), "r"(sd));
}

#define NEARLY 0
#define XAHEAD 3
#define WAFTER 3
#define WPACE 50
#define GATE_AT 0
#define TPACE 40
#define PFMODE 0
#define MAPMODE 0
template <int V> struct IC { static constexpr int value = V; };
struct Maps { CUtensorMap ft, g32, x, u32, wr, wi, g64, u64, e, xs, ts, t, d192, d32; };

constexpr int NCTA = 130;
constexpr int U = 16384;
constexpr int TB = 36864;
constexpr int NR = 4;
constexpr int OFF_RING = 8 * U, OFF_Z = 9 * U, OFF_XB = 12 * U, OFF_T = 13 * U, OFF_D = OFF_T + 8192;
constexpr int OFF_BAR = 14 * U;
constexpr int SMEM_BYTES = OFF_BAR + 512;
constexpr int B_FX = 0, B_FA = 8, B_FT = 12, B_Z = 16, B_W = 20, B_HX = 21, B_TL = 22, B_HP = 23, B_WR = 26;
constexpr int B_EA = 27, B_ET = 31, B_RDY = 35;
constexpr int B_T = 36, B_WD = 37, B_XS = 38, NBAR = 39;
__host__ __device__ constexpr int rslot(int n) { return n % NR; }
__host__ __device__ constexpr int rpar(int n) { return (n / NR) & 1; }

__global__ void __cluster_dims__(2, 1, 1) __launch_bounds__(512, 1)
fused_kernel(const __grid_constant__ Maps maps, const __nv_bfloat16* __restrict__ x, const __nv_bfloat16* __restrict__ w_r,
             const __nv_bfloat16* __restrict__ w_i, const __nv_bfloat16* __restrict__ gate_w, const __nv_bfloat16* __restrict__ Wg,
             const __nv_bfloat16* __restrict__ Wu, __nv_bfloat16* __restrict__ out) {
  extern __shared__ __align__(1024) uint8_t smem[];
  const uint32_t sb = smem_u32(smem);
  const uint32_t bars = sb + OFF_BAR;
  const int tid = threadIdx.x, lane = tid & 31;
  const int warp = __shfl_sync(0xffffffffu, tid >> 5, 0);
  const bool helper = blockIdx.x >= 128;
  const int cl = (blockIdx.x >> 1) & 63, rank = blockIdx.x & 1;
  const int q4 = cl & 3, rb = cl >> 2;
  const int j = 2 * q4 + rank;
  const int f_full = 448 * q4 + (rank ? 256 : 0);
  const int f_half = 448 * q4 + (rank ? 224 : 192);
  const int kg = 2 * j + (rb >> 3), tn = rb & 7;

  if (tid == 64) { PROF_EV(0); PROF_CK(40); }
  auto ring_part = [&](int p, int n, int slot) {
    const uint32_t fb = bars + 8 * (B_FA + slot), dst = sb + OFF_RING + slot * U;
    const bool table = n == 9 || n == 10 || n >= 34;
    const int q = n == 8 ? 0 : n - 10;
    if (p == 0) {
      mbar_expect_tx(fb, U);
      if (n < 8) tma2d(dst, &maps.ft, fb, 64 * n, 64 * j);
      else if (table) tma4d(dst, &maps.e, fb, 0, 0, 0, 2 * rb + (n >= 34 ? n - 34 : n - 9));
      else tma2d(dst, &maps.g64, fb, f_full + 64 * (q >> 3), 64 * (q & 7));
    } else if (p == 1) {
      if (n < 8) { tma2d(dst + 8192, &maps.g32, fb, f_half, 64 * n); tma2d(dst + 12288, &maps.u32, fb, f_half, 64 * n); }
      else if (!table) tma2d(dst + 8192, &maps.u64, fb, f_full + 64 * (q >> 3), 64 * (q & 7));
    }
  };
  auto x_load = [&](int q) {
    mbar_expect_tx(bars + 8 * (B_FX + q), U);
    tma3d(sb + q * U, &maps.x, bars + 8 * (B_FX + q), 64 * q, 0, 2 * rb);
  };
  if (warp < 8) {
    if (!helper) {
      const int r8 = tid >> 3, c8 = tid & 7, r4 = tid >> 2, c4 = tid & 3;
      const uint32_t sw8 = r8 * 128 + ((c8 ^ (r8 & 7)) << 4), sw4 = r4 * 64 + ((c4 ^ ((r4 >> 1) & 3)) << 4);
      const __nv_bfloat16* px = x + (size_t)(2 * rb + 32 * r8) * 512 + 8 * c8;
      const uint16_t* pf = g_FT.v + (64 * j + r8) * 512 + 8 * c8;
      const size_t om = (size_t)r4 * 1792 + f_half + 8 * c4;
#pragma unroll
      for (int kb = 0; kb < NEARLY; kb++) {
        const uint32_t dst = sb + OFF_RING + rslot(kb) * U;
#pragma unroll
        for (int i = 0; i < 4; i++) cp16(sb + kb * U + i * 4096 + sw8, px + (i & 1) * 32 * 32 * 512 + (i >> 1) * 512 + 64 * kb);
        cp16(dst + sw8, pf + 64 * kb); cp16(dst + 4096 + sw8, pf + 32 * 512 + 64 * kb);
        cp16(dst + 8192 + sw4, Wg + om + kb * 64 * 1792); cp16(dst + 12288 + sw4, Wu + om + kb * 64 * 1792);
        asm volatile("cp.async.commit_group;" ::: "memory");
      }
    }
  } else if (warp < 12) {
    if (lane == 0) {
#pragma unroll
      for (int i = 0; i < 4; i++) if (warp - 8 + 4 * i < 14) asm volatile("prefetch.tensormap [%0];" ::"l"((const char*)&maps + (warp - 8 + 4 * i) * 128) : "memory");
    }
  } else if (lane == 0) {
    if (warp == 15) {
#pragma unroll
      for (int i = B_FT; i < NBAR; i++) mbar_init(bars + 8 * i, i < B_EA ? 1 : i < B_T ? 2 : i < B_XS ? 4 : 8);
#pragma unroll
      for (int i = 0; i < 4; i++) mbar_expect_tx(bars + 8 * (B_Z + i), U);
      asm volatile("fence.mbarrier_init.release.cluster;" ::: "memory");
    } else if (warp == 14) {
#pragma unroll
      for (int i = 0; i < B_FT; i++) mbar_init(bars + 8 * i, 1);
#pragma unroll
      for (int i = 0; i < NEARLY; i++) mbar_arrive(bars + 8 * (B_FA + rslot(i)));
    }
    asm volatile("fence.proxy.async.shared::cta;" ::: "memory");
  }
  if (warp >= 12) {
    __syncwarp();
    asm volatile("bar.arrive 0, 384;" ::: "memory");
    asm volatile("bar.arrive 4, 256;" ::: "memory");
    asm volatile("bar.sync 3, 128;" ::: "memory");
  }
  asm volatile("barrier.cluster.arrive.relaxed.aligned;" ::: "memory");
  if (tid == 64) PROF_EV(38);

  if (warp >= 12) {
    asm volatile("setmaxnreg.dec.sync.aligned.u32 24;");
    if (lane == 0 && (!helper || warp == 15)) {
      if (warp < 14) {
        int slot = rslot(NEARLY), par = 1;
#pragma unroll 1
        for (int n = NEARLY; n < 36; n++) {
          if (n >= NEARLY + XAHEAD && n < NR) mbar_wait(bars + 8 * (B_FX + n - XAHEAD), 0);
          mbar_wait(bars + 8 * (B_EA + slot), par);
          ring_part(warp - 12, n, slot);
          if (++slot == NR) { slot = 0; par ^= 1; }
        }
      } else if (warp == 15) {
        const unsigned ep1 = ld_x1(&g_epoch[blockIdx.x * 8]) + 1;
        mbar_expect_tx(bars + 8 * B_W, 8192);
        bulk_load(sb + OFF_D, g_DT.v, 8192, bars + 8 * B_W);
        if (!helper) {
          mbar_wait(bars + 8 * (B_FX + WAFTER), 0);
          mbar_expect_tx(bars + 8 * B_WR, 24576);
#pragma unroll 1
          for (int i = 0; i < 8; i++) { tma4d(sb + OFF_XB + i * 3072, i < 4 ? &maps.wr : &maps.wi, bars + 8 * B_WR, 16 * kg, 0, 2 * (i & 3), tn); __nanosleep(WPACE); }
        }
        flag_wait(&g_cntX[helper ? 0 : 32 * j], ep1 * 16u);
        PROF_EV(22);
        mbar_expect_tx(bars + 8 * B_HX, U);
        bulk_load(sb + OFF_XB, g_X + (size_t)(helper ? 128 : kg * 8 + tn) * 8192, U, bars + 8 * B_HX);
        if (!helper) {
          flag_wait(&g_cntT[32 * j], ep1 * 16u);
          PROF_EV(23);
          mbar_expect_tx(bars + 8 * B_TL, U);
          tma3d(sb + OFF_T, &maps.t, bars + 8 * B_TL, 64 * j, 0, 2 * rb);
#pragma unroll 1
          for (int i = 0; i < 3; i++) { hint_wait(&g_cntP[32 * (rb * 8 + j) + i], ep1 * 8u); mbar_arrive(bars + 8 * (B_HP + i)); }
        }
      } else {
#pragma unroll 1
        for (int q = NEARLY; q < 8; q++) { if (q >= NEARLY + XAHEAD) mbar_wait(bars + 8 * (B_FX + q - XAHEAD), 0); x_load(q); }
        PROF_EV(31);
        mbar_wait(bars + 8 * B_XS, 0);
#pragma unroll
        for (int h2 = 0; h2 < 2; h2++) {
          const int s0 = 2 * rb + h2, sg = (s0 & ~6) | ((s0 & 2) << 1) | ((s0 & 4) >> 1);
          asm volatile("cp.async.bulk.tensor.4d.global.shared::cta.bulk_group [%0, {%2, %3, %4, %5}], [%1];" ::"l"(&maps.xs), "r"(sb + OFF_XB + h2 * 8192),
                       "r"(0), "r"(sg), "r"(0), "r"(16 * j) : "memory");
          if (j == 0) {
#pragma unroll
            for (int c = 0; c < 2; c++)
              asm volatile("cp.async.bulk.global.shared::cta.bulk_group [%0], [%1], 256;" ::"l"(g_X + 128 * 8192 + c * 4096 + sg * 128),
                           "r"(sb + OFF_T + h2 * 512 + c * 256) : "memory");
          }
        }
        bulk_done_signal(&g_cntX[32 * j]);
        PROF_EV(20);
#pragma unroll 1
        for (int t = 0; t < 8; t++) {
          const int i = t < 3 ? t + 1 : t < 6 ? t - 2 : 0;
          const int col = 64 * (2 * ((q4 + i) & 3) + ((t < 3 || t == 6) ? 1 - rank : rank));
          const uint32_t fb = bars + 8 * (B_FT + (t & 3)), dst = sb + (t & 3) * TB;
          mbar_wait(bars + 8 * (B_ET + (t & 3)), t >> 2);
          mbar_expect_tx(fb, TB);
          tma2d(dst, &maps.d192, fb, col, f_full);
          tma2d(dst + 24576, &maps.d32, fb, col, f_half);
          tma2d(dst + 28672, &maps.ft, fb, col, 64 * j);
        }
      }
    }
  } else if (warp >= 8) {
    asm volatile("setmaxnreg.dec.sync.aligned.u32 104;");
    const int t = tid - 256, w = warp - 8;
    const uint32_t ep = ld_x1(&g_epoch[blockIdx.x * 8]);
    const uint32_t tag = (ep + 1) & 1;
    auto gate_rows = [&] {
      uint4 xv[8], gv[2];
#pragma unroll
      for (int i = 0; i < 4; i++) {
        const int r = 16 * j + 4 * w + i;
        const uint4* p = (const uint4*)(x + (size_t)(2 * rb + (r >> 6) + 32 * (r & 63)) * 512) + lane;
        xv[2 * i] = __ldg(p); xv[2 * i + 1] = __ldg(p + 32);
      }
      gv[0] = __ldg((const uint4*)gate_w + lane); gv[1] = __ldg((const uint4*)gate_w + lane + 32);
      {
        float z[4];
#pragma unroll
        for (int i = 0; i < 4; i++) {
          float a = 0.f;
#pragma unroll
          for (int hh = 0; hh < 2; hh++) {
            const uint4 u = xv[2 * i + hh], v = gv[hh];
            a = fmaf(bf_lo(u.x), bf_lo(v.x), a); a = fmaf(bf_hi(u.x), bf_hi(v.x), a);
            a = fmaf(bf_lo(u.y), bf_lo(v.y), a); a = fmaf(bf_hi(u.y), bf_hi(v.y), a);
            a = fmaf(bf_lo(u.z), bf_lo(v.z), a); a = fmaf(bf_hi(u.z), bf_hi(v.z), a);
            a = fmaf(bf_lo(u.w), bf_lo(v.w), a); a = fmaf(bf_hi(u.w), bf_hi(v.w), a);
          }
#pragma unroll
          for (int o = 16; o; o >>= 1) a += __shfl_xor_sync(0xffffffffu, a, o);
          z[i] = a;
        }
        if (lane < 4) {
          const float zz = lane == 0 ? z[0] : lane == 1 ? z[1] : lane == 2 ? z[2] : z[3];
          asm volatile("st.relaxed.gpu.global.f32 [%0], %1;" ::"l"(g_gate + rb * 128 + 16 * j + 4 * w + lane), "f"(tagf(1.0f / (1.0f + __expf(-zz)), tag)) : "memory");
        }
        if (t == 0) PROF_EV(18);
      }
      if (w == 0) {
        const int c = lane >> 4, jj = 16 * blockIdx.x + (lane & 15), jm = (2048 - jj) & 2047;
        const unsigned short* pr = (const unsigned short*)w_r + 256 * c;
        const unsigned short* pi = (const unsigned short*)w_i + 256 * c;
        const float wr = 0.25f * (bf_lo(__ldg(pr + jj * 257)) + bf_lo(__ldg(pr + jm * 257)));
        const float wi = 0.25f * (bf_lo(__ldg(pi + jj * 257)) - bf_lo(__ldg(pi + jm * 257)));
        st_u2(g_Wh + c * 2048 + jj, c ? pack_bf16(-wi, wr) : pack_bf16(wr, wi), tag);
        __syncwarp();
        if (lane == 0) hint_add(&g_cntW[0]);
      }
    };
    {
      const int g = lane >> 2, q = lane & 3;
      uint32_t wf[32];
      if (!helper) {
        gate_rows();
        asm volatile("bar.sync 4, 256;" ::: "memory");
        const uint32_t wa = sb + OFF_XB + w * (3072 + 4) + q * 48 + g * 2;
        mbar_wait(bars + 8 * B_WR, 0);
#pragma unroll
        for (int n = 0; n < 8; n++) {
          uint32_t v[8];
#pragma unroll
          for (int i = 0; i < 8; i++)
            asm volatile("ld.shared.u16 %0, [%1];" : "=r"(v[i]) : "r"(wa + n * 192 + (i & 1) * 12288 + ((i >> 1) & 1) * (1536 + 2) + (i >> 2) * 16) : "memory");
#pragma unroll
          for (int i = 0; i < 4; i++) {
            wf[(i >> 1) * 16 + 2 * n + (i & 1)] = v[2 * i] | (v[2 * i + 1] << 16);
            asm volatile("" : "+r"(wf[(i >> 1) * 16 + 2 * n + (i & 1)])::"memory");
          }
        }
        __syncwarp();
        if (lane == 0) mbar_arrive(bars + 8 * B_WD);
        if (t == 0) PROF_EV(11);
      } else {
        asm volatile("bar.sync 4, 256;" ::: "memory");
        hint_wait(&g_cntW[0], (ep + 1) * 128u);
        const uint32_t t0 = (uint32_t)clock();
#pragma unroll 1
        for (;;) {
          uint32_t bad = 0;
#pragma unroll
          for (int i = 0; i < 32; i++) {
            const float2 v = ld_x2((const float2*)g_Wh + (i >> 4) * 2048 + 16 * w + g + 8 * (i & 1) + 64 * q + ((i >> 1) & 7) * 256);
            wf[i] = __float_as_uint(v.x); bad |= __float_as_uint(v.y) ^ tag;
          }
          if (!__any_sync(0xffffffffu, bad & 1)) break;
          spin_guard(t0);
        }
        if (t == 0) PROF_EV(11);
      }
      mbar_wait(bars + 8 * B_W, 0);
      mbar_wait(bars + 8 * B_HX, 0);
      if (t == 0) PROF_EV(12);
      const uint32_t dd = (sb & 0x3FFFF) >> 4;
      const uint64_t dF = d128((dd + (OFF_D >> 4)) | (512u << 16)), dI = d128((dd + (OFF_D >> 4)) | (1u << 16)), dA = d128((dd + (OFF_XB >> 4)) | (512u << 16));
      float az[32];
      const int zero = blockIdx.x >> 16;
      uint32_t pf[32];
#pragma unroll
      for (int mt = 0; mt < 2; mt++) {
        wg_fence();
        if (mt == 0) mma_ss64<0, 3, 0>(az, dA, dF);
        else mma_ss64<0, 3, 2>(az, dA + 512, dF, zero);
#pragma unroll
        for (int k = 1; k < 4; k++) mma_ss64<0, 3, 1>(az, dA + (mt * 512 + k * 128), dF + k * 128);
        wg_commit();
        wg_wait<0>();
        fence_regs<0, 32>(az);
#pragma unroll
        for (int i = 0; i < 16; i++) {
          const float wr = bf_lo(wf[16 * mt + i]), wi = bf_hi(wf[16 * mt + i]);
          pf[16 * mt + i] = pack_pin(fmaf(az[2 * i], wr, -az[2 * i + 1] * wi), fmaf(az[2 * i], wi, az[2 * i + 1] * wr));
        }
      }
      if (t == 0) PROF_EV(16);
#pragma unroll
      for (int mt = 0; mt < 2; mt++) {
        wg_fence();
        mma_rs64<0, 0, 2>(az, pf[16 * mt], pf[16 * mt + 1], pf[16 * mt + 2], pf[16 * mt + 3], dI, mt ? (int)helper : zero);
#pragma unroll
        for (int k = 1; k < 4; k++) mma_rs64<0, 0, 1>(az, pf[16 * mt + 4 * k], pf[16 * mt + 4 * k + 1], pf[16 * mt + 4 * k + 2], pf[16 * mt + 4 * k + 3], dI + k * 2);
        wg_commit();
        wg_wait<0>();
        fence_regs<0, 32>(az);
        if (!helper) {
          const int m = lane >> 3, r = lane & 7;
          const int sl = 2 * (m >> 1) + ((r >> 1) & 1) + 4 * (r >> 2);
          const uint32_t a0 = sb + OFF_XB + (2 * w + (m & 1)) * 2048 + sl * 64 + (((mt * 2 + (r & 1)) ^ (sl >> 1)) << 4);
#pragma unroll
          for (int i = 0; i < 4; i++)
            stsm4t(a0 + i * 512, pack_bf16(az[8 * i], az[8 * i + 1]), pack_bf16(az[8 * i + 2], az[8 * i + 3]), pack_bf16(az[8 * i + 4], az[8 * i + 5]),
                   pack_bf16(az[8 * i + 6], az[8 * i + 7]));
        }
      }
      if (helper) {
#pragma unroll
        for (int i = 0; i < 16; i++) {
          const int n = i >> 1, s0 = 8 * (n >> 1) + 2 * (n & 1) + (q & 1) + 4 * (q >> 1);
          if ((n & 1) == (int)(blockIdx.x & 1)) st_u2(g_Ts + s0 * 64 + 16 * w + g + 8 * (i & 1), pack_bf16(az[2 * i], az[2 * i + 1]), tag);
        }
        __syncwarp();
        if (lane == 0) hint_add(&g_cntH[0]);
        if (t == 0) { g_epoch[blockIdx.x * 8] = ep + 1; PROF_EV(13); }
      } else {
        asm volatile("fence.proxy.async.shared::cta;" ::: "memory");
        asm volatile("bar.sync 1, 128;" ::: "memory");
        if (t == 0) {
          PROF_EV(17);
          asm volatile("cp.async.bulk.tensor.3d.global.shared::cta.bulk_group [%0, {%2, %3, %4}], [%1];" ::"l"(&maps.ts), "r"(sb + OFF_XB),
                       "r"(32 * kg), "r"(0), "r"(8 * tn) : "memory");
          bulk_done_signal(&g_cntT[32 * j]);
          PROF_EV(13);
        }
        __syncwarp();
        if (j == 0) {
          hint_wait(&g_cntH[0], (ep + 1) * 8u);
          const uint32_t t0 = (uint32_t)clock();
          float2 v;
          do { v = ld_x2((const float2*)g_Ts + 2 * rb * 64 + t); spin_guard(t0); } while (__any_sync(0xffffffffu, (__float_as_uint(v.y) ^ tag) & 1));
          mbar_wait(bars + 8 * B_TL, 0);
          const uint32_t u = __float_as_uint(v.x);
          *(uint16_t*)(smem + OFF_T + t * 128 + ((t & 7) << 4)) = (uint16_t)u;
          *(uint16_t*)(smem + OFF_T + t * 128 + (((t & 7) ^ 1) << 4)) = (uint16_t)(u >> 16);
          asm volatile("fence.proxy.async.shared::cta;" ::: "memory");
          __syncwarp();
          if (lane == 0) mbar_arrive(bars + 8 * B_T);
        }
      }
    }
  } else {
    asm volatile("setmaxnreg.inc.sync.aligned.u32 192;");
    if (!helper) {
      const int wg = warp >> 2, w = warp & 3, g = lane >> 2, q = lane & 3;
      const bool elect = (tid & 127) == 0;
      const uint32_t ep = ld_x1(&g_epoch[blockIdx.x * 8]);
      float c1[64], cA[64], c2[64], ci[64], ct[64];
      const int zero = blockIdx.x >> 16;
      uint32_t h[56], yf[16];
      const uint32_t d0 = (sb & 0x3FFFF) >> 4;
      const uint32_t dK = d0 | (1u << 16), dN = d0 | (512u << 16), dM = d0 | (256u << 16);
      const uint32_t dX = dK + wg * 512;
      constexpr uint32_t RING = OFF_RING >> 4;
      auto waitA = [&](int n) { mbar_wait(bars + 8 * (B_FA + rslot(n)), rpar(n)); };
      auto freeA = [&](int n) { if (elect) mbar_arrive(bars + 8 * (B_EA + rslot(n))); };
      auto nop = [](int) {};

#pragma unroll
      for (int kb = 0; kb < 8; kb++) {
        if (kb < NEARLY) {
          if (NEARLY - 1 - kb == 3) asm volatile("cp.async.wait_group 3;" ::: "memory");
          else if (NEARLY - 1 - kb == 2) asm volatile("cp.async.wait_group 2;" ::: "memory");
          else if (NEARLY - 1 - kb == 1) asm volatile("cp.async.wait_group 1;" ::: "memory");
          else asm volatile("cp.async.wait_group 0;" ::: "memory");
          asm volatile("fence.proxy.async.shared::cta;" ::: "memory");
          if (kb == 0) asm volatile("bar.sync 0, 384;" ::: "memory");
          else asm volatile("bar.sync 2, 256;" ::: "memory");
        } else {
          if (kb == 0) asm volatile("bar.sync 0, 384;" ::: "memory");
          mbar_wait(bars + 8 * (B_FX + kb), 0); waitA(kb);
        }
        wg_fence();
        const uint64_t dx = d128(dX + kb * 1024), df = d128(dK + RING + rslot(kb) * 1024), dm = d64(dM + RING + 512 + rslot(kb) * 1024);
        if (kb == 0) { mma_ss64<0, 0, 0>(c1, df, dx); mma_ss64<32, 1, 0>(c1, dx, dm); }
        else { mma_ss64<0, 0, 1>(c1, df, dx); mma_ss64<32, 1, 1>(c1, dx, dm); wg_commit(); wg_wait<1>(); freeA(kb - 1); }
#pragma unroll
        for (int k = 1; k < 4; k++) {
          mma_ss64<0, 0, 1>(c1, df + k * 2, dx + k * 2);
          mma_ss64<32, 1, 1>(c1, dx + k * 2, dm + k * 64);
        }
        wg_commit();
        if (kb == 0 && tid == 0) PROF_EV(1);
      }
      auto ffn_step = [&](auto first, float (&acc)[64], int n, int kb, auto done, auto work) {
        waitA(n);
        wg_fence();
        const uint64_t dx = d128(dX + kb * 1024), db = d128(dN + RING + rslot(n) * 1024);
        mma_ss128<0, 1, decltype(first)::value>(acc, dx, db, zero);
        wg_commit();
        wg_wait<1>();
        done();
#pragma unroll
        for (int k = 1; k < 4; k++) { mma_ss128<0, 1, 1>(acc, dx + k * 2, db + k * 128); work(k - 1); }
        wg_commit();
        work(3);
      };
      const uint32_t tag = (ep + 1) & 1;
      float hm[16];
      ffn_step(IC<0>(), c2, 8, 0, [&] { freeA(7); fence_regs<0, 64>(c1); }, [&](int i) {
#pragma unroll
        for (int e = 4 * i; e < 4 * i + 4; e++) { yf[e] = pack_pin(c1[2 * e], c1[2 * e + 1]); hm[e] = fmaxf(c1[32 + e], 0.f) * c1[48 + e]; }
      });
      fence_regs<0, 16>(hm);
      if (tid == 0) PROF_EV(2);
      {
        waitA(9); waitA(10);
        const uint64_t de = d128(dN + RING + (wg ? rslot(10) : rslot(9)) * 1024);
        wg_fence();
        mma_rs128<0, 1, 0>(cA, yf[0], yf[1], yf[2], yf[3], de);
        wg_commit();
        wg_wait<1>();
        freeA(8);
#pragma unroll
        for (int k = 1; k < 4; k++) mma_rs128<0, 1, 1>(cA, yf[4 * k], yf[4 * k + 1], yf[4 * k + 2], yf[4 * k + 3], de + k * 128);
        wg_commit();
      }
      {
        const int s0 = 2 * rb + wg, kr = 2 * ((s0 & 1) | ((s0 & 4) >> 1));
        const int m = lane >> 3, r = lane & 7;
        const uint32_t a0 = sb + OFF_XB + wg * 8192 + (((w >> 1) * 8 + (m >> 1)) * 2 + (w & 1)) * 256 + (m & 1) * 128 + ((r ^ (kr + (m & 1))) << 4);
        ffn_step(IC<1>(), c2, 11, 1, [&] { freeA(9); freeA(10); mbar_wait(bars + 8 * B_WD, 0); fence_regs<0, 64>(cA); }, [&](int i) {
          stsm4t(a0 + i * 1024, pack_bf16(cA[8 * i] - cA[34 + 8 * i], cA[8 * i + 1] - cA[35 + 8 * i]),
                 pack_bf16(cA[32 + 8 * i] + cA[8 * i + 2], cA[33 + 8 * i] + cA[8 * i + 3]),
                 pack_bf16(cA[8 * i + 4] - cA[38 + 8 * i], cA[8 * i + 5] - cA[39 + 8 * i]),
                 pack_bf16(cA[36 + 8 * i] + cA[8 * i + 6], cA[37 + 8 * i] + cA[8 * i + 7]));
        });
        if (j == 0 && w == 0 && g == 0) {
#pragma unroll
          for (int n = 0; n < 8; n++)
#pragma unroll
            for (int ce = 0; ce < 4; ce++)
              *(uint32_t*)(smem + OFF_T + wg * 512 + ce * 128 + ((n ^ (kr + (ce & 1))) << 4) + 4 * q) =
                  pack_bf16(cA[(ce & 1) * 32 + 4 * n + (ce & 2)], cA[(ce & 1) * 32 + 4 * n + (ce & 2) + 1]);
        }
        asm volatile("fence.proxy.async.shared::cta;" ::: "memory");
        __syncwarp();
        if (lane == 0) mbar_arrive(bars + 8 * B_XS);
        if (tid == 0) PROF_EV(3);
      }
      const float* gp = g_gate + rb * 128 + wg * 64 + w * 16 + g;
      uint32_t gb0 = ld_x1(gp), gb1 = ld_x1(gp + 8);
#pragma unroll
      for (int kb = 2; kb < 7; kb++) ffn_step(IC<1>(), c2, 10 + kb, kb, [&] { freeA(9 + kb); }, nop);
      {
        const uint32_t t0 = (uint32_t)clock();
        while (__any_sync(0xffffffffu, ((gb0 ^ tag) | (gb1 ^ tag)) & 1)) { gb0 = ld_x1(gp); gb1 = ld_x1(gp + 8); spin_guard(t0); }
      }
      const float g0 = __uint_as_float(gb0 & ~1u), g1 = __uint_as_float(gb1 & ~1u);
      const float o0 = 1.0f - g0, o1 = 1.0f - g1;
      uint32_t hp[8];
      ffn_step(IC<1>(), c2, 17, 7, [&] { freeA(16); }, [&](int i) {
        hp[2 * i] = pack_pin(hm[4 * i] * o0, hm[4 * i + 1] * o0); hp[2 * i + 1] = pack_pin(hm[4 * i + 2] * o1, hm[4 * i + 3] * o1);
      });
      auto glu = [&](float (&acc)[64], int ho, int i0, int i1) {
#pragma unroll
        for (int i = i0; i < i1; i++) {
          const float o = (i & 1) ? o1 : o0;
          h[ho + i] = pack_pin(fmaxf(acc[2 * i], 0.f) * acc[32 + 2 * i] * o, fmaxf(acc[2 * i + 1], 0.f) * acc[33 + 2 * i] * o);
        }
      };
      ffn_step(IC<2>(), cA, 18, 0, [&] { freeA(17); fence_regs<0, 64>(c2); }, [&](int i) { glu(c2, 0, 2 * i, 2 * i + 2); });
      if (tid == 0) PROF_EV(4);
      ffn_step(IC<1>(), cA, 19, 1, [&] { freeA(18); }, [&](int i) { glu(c2, 0, 8 + 2 * i, 10 + 2 * i); });
#pragma unroll
      for (int kb = 2; kb < 8; kb++) ffn_step(IC<1>(), cA, 18 + kb, kb, [&] { freeA(17 + kb); }, nop);
      ffn_step(IC<2>(), c2, 26, 0, [&] { freeA(25); fence_regs<0, 64>(cA); }, [&](int i) { glu(cA, 16, 2 * i, 2 * i + 2); });
      if (tid == 0) PROF_EV(5);
      ffn_step(IC<1>(), c2, 27, 1, [&] { freeA(26); }, [&](int i) { glu(cA, 16, 8 + 2 * i, 10 + 2 * i); });
#pragma unroll
      for (int kb = 2; kb < 8; kb++)
        ffn_step(IC<1>(), c2, 26 + kb, kb, [&] {
          if (kb < 7) freeA(25 + kb);
          if (kb >= 3 && (kb & 1) && elect) mbar_arrive(bars + 8 * (B_ET + ((kb - 3) >> 1)));
        }, nop);
      wg_wait<0>();
      if (elect) mbar_arrive(bars + 8 * (B_ET + 3));
      fence_regs<0, 64>(c2);
      glu(c2, 32, 0, 16);
#pragma unroll
      for (int i = 0; i < 8; i++) h[48 + i] = hp[i] ^ zero;
      if (wg) waitA(35); else waitA(34);
      if (tid == 0) PROF_EV(6);
      mbar_wait(bars + 8 * (j == 0 ? B_T : B_TL), 0);
      if (tid == 0) PROF_EV(7);
      wg_fence();
      {
        const uint64_t dt = d128(dN + (OFF_T >> 4) + wg * 512), de = d128(dK + RING + (wg ? rslot(35) : rslot(34)) * 1024);
        mma_ss64<0, 1, 0>(ci, de, dt);
        mma_ss64<32, 1, 0>(ci, de + 512, dt);
#pragma unroll
        for (int k = 1; k < 4; k++) {
          mma_ss64<0, 1, 1>(ci, de + k * 2, dt + k * 128);
          mma_ss64<32, 1, 1>(ci, de + (512 + k * 2), dt + k * 128);
        }
      }
      wg_commit();

      auto head = [&](auto off, int t) {
        constexpr int O = decltype(off)::value;
        mbar_wait(bars + 8 * (B_FT + (t & 3)), t >> 2);
        const uint64_t db = d128(dN + (t & 3) * (TB >> 4));
        wg_fence();
        mma_rs64<O, 1, 0>(ct, h[0], h[1], h[2], h[3], db);
#pragma unroll
        for (int k = 1; k < 6; k++) mma_rs64<O, 1, 1>(ct, h[4 * k], h[4 * k + 1], h[4 * k + 2], h[4 * k + 3], db + k * 128);
        wg_commit();
        wg_wait<1>();
      };
      auto rest = [&](auto off, int t) {
        constexpr int O = decltype(off)::value;
        const uint64_t db = d128(dN + (t & 3) * (TB >> 4));
        wg_fence();
#pragma unroll
        for (int k = 6; k < 14; k++) mma_rs64<O, 1, 1>(ct, h[4 * k], h[4 * k + 1], h[4 * k + 2], h[4 * k + 3], db + k * 128);
#pragma unroll
        for (int k = 0; k < 4; k++) mma_rs64<O, 1, 1>(ct, yf[4 * k], yf[4 * k + 1], yf[4 * k + 2], yf[4 * k + 3], db + (14 + k) * 128);
        wg_commit();
      };
      auto freeT = [&](int t) { if (elect) mbar_arrive(bars + 8 * (B_ET + t)); };
      const uint32_t peerZ = mapa(sb + OFF_Z + tid * 16, rank ^ 1), peerB = mapa(bars + 8 * B_Z, rank ^ 1);
      auto send_peer = [&](auto off, int z) {
        constexpr int O = decltype(off)::value;
        fence_regs<O, 32>(ct);
#pragma unroll
        for (int i = 0; i < 4; i++)
          asm volatile("st.async.weak.shared::cluster.mbarrier::complete_tx::bytes.v4.b32 [%0], {%1,%2,%3,%4}, [%5];" ::"r"(peerZ + z * U + i * 4096),
                       "r"(pack_bf16(ct[O + 8 * i], ct[O + 8 * i + 1])), "r"(pack_bf16(ct[O + 8 * i + 2], ct[O + 8 * i + 3])),
                       "r"(pack_bf16(ct[O + 8 * i + 4], ct[O + 8 * i + 5])), "r"(pack_bf16(ct[O + 8 * i + 6], ct[O + 8 * i + 7])), "r"(peerB + 8 * z) : "memory");
      };
      auto send_grid = [&](auto off, int z) {
        constexpr int O = decltype(off)::value;
        fence_regs<O, 32>(ct);
        mbar_wait(bars + 8 * (B_Z + z), 0);
        uint4* dst = g_part + (size_t)((rb * 8 + 2 * ((q4 + z + 1) & 3) + rank) * 3 + z) * 1024 + tid;
#pragma unroll
        for (int i = 0; i < 4; i++) {
          const uint4 p = *(const uint4*)(smem + OFF_Z + z * U + i * 4096 + tid * 16);
          st_x4(dst + i * 256, (pack_bf16(ct[O + 8 * i] + bf_lo(p.x), ct[O + 8 * i + 1] + bf_hi(p.x)) & ~1u) | tag,
                pack_bf16(ct[O + 8 * i + 2] + bf_lo(p.y), ct[O + 8 * i + 3] + bf_hi(p.y)),
                pack_bf16(ct[O + 8 * i + 4] + bf_lo(p.z), ct[O + 8 * i + 5] + bf_hi(p.z)),
                pack_bf16(ct[O + 8 * i + 6] + bf_lo(p.w), ct[O + 8 * i + 7] + bf_hi(p.w)));
        }
        __syncwarp();
        if (lane == 0) hint_add(&g_cntP[32 * (rb * 8 + 2 * ((q4 + z + 1) & 3) + rank) + z]);
      };
      asm volatile("barrier.cluster.wait.aligned;" ::: "memory");
      head(IC<0>(), 0);
      if (elect) asm volatile("mbarrier.arrive.shared::cluster.b64 _, [%0];" ::"r"(mapa(bars + 8 * B_RDY, rank ^ 1)) : "memory");
      fence_regs<0, 64>(ci);
#pragma unroll
      for (int i = 0; i < 16; i++) {
        const float gg = ((i & 1) ? g1 : g0) * (2.0f / (2048.0f * 512.0f));
        if (i & 2) yf[i] = pack_pin((ci[2 * i] - ci[28 + 2 * i]) * gg, (ci[2 * i + 1] - ci[29 + 2 * i]) * gg);
        else yf[i] = pack_pin((ci[2 * i] + ci[36 + 2 * i]) * gg, (ci[2 * i + 1] + ci[37 + 2 * i]) * gg);
      }
      rest(IC<0>(), 0);
      if (tid == 0) PROF_EV(8);
      head(IC<32>(), 1); freeT(0); mbar_wait(bars + 8 * B_RDY, 0); send_peer(IC<0>(), 0); rest(IC<32>(), 1);
      head(IC<0>(), 2); freeT(1); send_peer(IC<32>(), 1); rest(IC<0>(), 2);
      head(IC<32>(), 3); freeT(2); send_peer(IC<0>(), 2); rest(IC<32>(), 3);
      head(IC<0>(), 4); freeT(3); send_grid(IC<32>(), 0); rest(IC<0>(), 4);
      head(IC<32>(), 5); send_grid(IC<0>(), 1); rest(IC<32>(), 5);
      head(IC<0>(), 6); send_grid(IC<32>(), 2); rest(IC<0>(), 6);
      head(IC<32>(), 7); send_peer(IC<0>(), 3);
      {
        const uint4* src = g_part + (size_t)(rb * 8 + j) * 3 * 1024 + tid;
        uint4 pv[12];
        mbar_wait(bars + 8 * (B_HP + 1), 0);
#pragma unroll
        for (int i = 0; i < 8; i++) pv[i] = ld_x4(src + i * 256);
        rest(IC<32>(), 7);
        if (tid == 0) PROF_EV(9);
        mbar_wait(bars + 8 * (B_HP + 2), 0);
        if (tid == 0) PROF_EV(24);
#pragma unroll
        for (int i = 8; i < 12; i++) pv[i] = ld_x4(src + i * 256);
        const uint32_t t0 = (uint32_t)clock();
        for (;;) {
          uint32_t bad = 0;
#pragma unroll
          for (int i = 0; i < 12; i++) bad |= pv[i].x ^ tag;
          if (!__any_sync(0xffffffffu, bad & 1)) break;
#pragma unroll
          for (int i = 0; i < 12; i++) pv[i] = ld_x4(src + i * 256);
          spin_guard(t0);
        }
        if (tid == 0) PROF_EV(14);
        float sum[32];
#pragma unroll
        for (int i = 0; i < 4; i++) {
          const uint32_t a[4] = {pv[i].x & ~1u, pv[i].y, pv[i].z, pv[i].w}, b[4] = {pv[4 + i].x & ~1u, pv[4 + i].y, pv[4 + i].z, pv[4 + i].w},
                         c[4] = {pv[8 + i].x & ~1u, pv[8 + i].y, pv[8 + i].z, pv[8 + i].w};
#pragma unroll
          for (int e = 0; e < 4; e++) {
            sum[8 * i + 2 * e] = bf_lo(a[e]) + bf_lo(b[e]) + bf_lo(c[e]);
            sum[8 * i + 2 * e + 1] = bf_hi(a[e]) + bf_hi(b[e]) + bf_hi(c[e]);
          }
        }
        mbar_wait(bars + 8 * (B_Z + 3), 0);
#pragma unroll
        for (int i = 0; i < 4; i++) {
          const uint4 p = *(const uint4*)(smem + OFF_Z + 3 * U + i * 4096 + tid * 16);
          const uint32_t a[4] = {p.x, p.y, p.z, p.w};
#pragma unroll
          for (int e = 0; e < 4; e++) { sum[8 * i + 2 * e] += bf_lo(a[e]); sum[8 * i + 2 * e + 1] += bf_hi(a[e]); }
        }
        wg_wait<0>();
        fence_regs<32, 32>(ct);
#pragma unroll
        for (int i = 0; i < 32; i++) sum[i] += ct[32 + i];
        const uint32_t stg = sb + OFF_T + warp * 2048;
        const int mr = (lane & 7) + ((lane >> 3) & 1) * 8, mc = lane >> 4;
#pragma unroll
        for (int i = 0; i < 4; i++) {
          const uint32_t a = stg + mr * 128 + (((2 * i + mc) ^ (mr & 7)) << 4);
          asm volatile("stmatrix.sync.aligned.m8n8.x4.shared.b16 [%0], {%1,%2,%3,%4};" ::"r"(a), "r"(pack_bf16(sum[8 * i], sum[8 * i + 1])),
                       "r"(pack_bf16(sum[8 * i + 2], sum[8 * i + 3])), "r"(pack_bf16(sum[8 * i + 4], sum[8 * i + 5])),
                       "r"(pack_bf16(sum[8 * i + 6], sum[8 * i + 7])) : "memory");
        }
        __syncwarp();
#pragma unroll
        for (int i = 0; i < 4; i++) {
          const int r = 4 * i + (lane >> 3), c = lane & 7;
          const uint4 v = *(const uint4*)(smem + OFF_T + warp * 2048 + r * 128 + ((c ^ (r & 7)) << 4));
          *(uint4*)(out + (size_t)(2 * rb + wg + 32 * (16 * w + r)) * 512 + 64 * j + 8 * c) = v;
        }
      }
      if (tid == 0) { g_epoch[blockIdx.x * 8] = ep + 1; PROF_EV(15); PROF_CK(41); }
    }
  }
}

typedef CUresult (*EncodeFn)(CUtensorMap*, CUtensorMapDataType, cuuint32_t, void*, const cuuint64_t*, const cuuint64_t*, const cuuint32_t*,
                             const cuuint32_t*, CUtensorMapInterleave, CUtensorMapSwizzle, CUtensorMapL2promotion, CUtensorMapFloatOOBfill);

static void encode(EncodeFn f, CUtensorMap* m, const void* base, int rank, const cuuint64_t* dims, const cuuint64_t* strides, const cuuint32_t* box,
                   CUtensorMapSwizzle sw) {
  cuuint32_t es[5] = {1, 1, 1, 1, 1};
  f(m, CU_TENSOR_MAP_DATA_TYPE_BFLOAT16, rank, (void*)base, dims, strides, box, es, CU_TENSOR_MAP_INTERLEAVE_NONE, sw,
    CU_TENSOR_MAP_L2_PROMOTION_L2_128B, CU_TENSOR_MAP_FLOAT_OOB_FILL_NONE);
}

extern "C" void kernel_launch(void* const* d_in, const int* in_sizes, int n_in, void* d_out, int out_size) {
  (void)in_sizes; (void)n_in; (void)out_size;
  const __nv_bfloat16* x = (const __nv_bfloat16*)d_in[0];
  const __nv_bfloat16* w_r = (const __nv_bfloat16*)d_in[1];
  const __nv_bfloat16* w_i = (const __nv_bfloat16*)d_in[2];
  const __nv_bfloat16* Wg = (const __nv_bfloat16*)d_in[4];
  const __nv_bfloat16* Wu = (const __nv_bfloat16*)d_in[5];
  const __nv_bfloat16* Wd = (const __nv_bfloat16*)d_in[6];
  const __nv_bfloat16* gw = (const __nv_bfloat16*)d_in[7];

  void* fp = nullptr; cudaDriverEntryPointQueryResult qr;
  cudaGetDriverEntryPoint("cuTensorMapEncodeTiled", &fp, cudaEnableDefault, &qr);
  EncodeFn enc = (EncodeFn)fp;
  void *pFT, *pET, *pX, *pT;
  cudaGetSymbolAddress(&pX, g_X); cudaGetSymbolAddress(&pT, g_T);
  cudaGetSymbolAddress(&pFT, g_FT); cudaGetSymbolAddress(&pET, g_ET);

  Maps mp;
  const CUtensorMapSwizzle S128 = CU_TENSOR_MAP_SWIZZLE_128B, S64 = CU_TENSOR_MAP_SWIZZLE_64B;
  { cuuint64_t d[3] = {512, 64, 32}, s[2] = {32768, 1024}; cuuint32_t b[3] = {64, 64, 2}; encode(enc, &mp.x, x, 3, d, s, b, S128); }
  { cuuint64_t d[2] = {512, 512}, s[1] = {1024}; cuuint32_t b[2] = {64, 64}; encode(enc, &mp.ft, pFT, 2, d, s, b, S128); }
  { cuuint64_t d[4] = {128, 32, 2, 129}, s[3] = {256, 8192, 16384}; cuuint32_t b[4] = {128, 1, 2, 16}; encode(enc, &mp.xs, pX, 4, d, s, b, CU_TENSOR_MAP_SWIZZLE_NONE); }
  { cuuint64_t d[3] = {512, 32, 64}, s[2] = {65536, 1024}; cuuint32_t b[3] = {32, 32, 8}; encode(enc, &mp.ts, pT, 3, d, s, b, S64); }
  { cuuint64_t d[3] = {512, 64, 32}, s[2] = {1024, 65536}; cuuint32_t b[3] = {64, 64, 2}; encode(enc, &mp.t, pT, 3, d, s, b, S128); }
  { cuuint64_t d[4] = {64, 64, 2, 32}, s[3] = {8192, 128, 256}; cuuint32_t b[4] = {64, 64, 2, 1}; encode(enc, &mp.e, pET, 4, d, s, b, S128); }
  { cuuint64_t d[2] = {1792, 512}, s[1] = {3584}; cuuint32_t b[2] = {64, 64}, b2[2] = {32, 64};
    encode(enc, &mp.g64, Wg, 2, d, s, b, S128); encode(enc, &mp.u64, Wu, 2, d, s, b, S128);
    encode(enc, &mp.g32, Wg, 2, d, s, b2, S64); encode(enc, &mp.u32, Wu, 2, d, s, b2, S64); }
  { cuuint64_t d[2] = {512, 1792}, s[1] = {1024}; cuuint32_t b[2] = {64, 192}, b2[2] = {64, 32};
    encode(enc, &mp.d192, Wd, 2, d, s, b, S128); encode(enc, &mp.d32, Wd, 2, d, s, b2, S128); }

  { cuuint64_t d[4] = {264, 32, 8, 8}, s[3] = {32896, 512, 4112}; cuuint32_t b[4] = {24, 32, 2, 1};
    encode(enc, &mp.wr, w_r, 4, d, s, b, CU_TENSOR_MAP_SWIZZLE_NONE); encode(enc, &mp.wi, w_i, 4, d, s, b, CU_TENSOR_MAP_SWIZZLE_NONE); }

  cudaFuncSetAttribute(fused_kernel, cudaFuncAttributeMaxDynamicSharedMemorySize, SMEM_BYTES);
  fused_kernel<<<NCTA, 512, SMEM_BYTES>>>(mp, x, w_r, w_i, gw, Wg, Wu, (__nv_bfloat16*)d_out);
}
```

```cpp
#include <cuda_runtime.h>
#include <cuda_bf16.h>
#include <cuda.h>
#include <stdint.h>

namespace tbl {
constexpr double PI = 3.14159265358979323846264338327950288;
constexpr double sin_s(double x) { double t = x, s = x; for (int n = 1; n < 12; n++) { t *= -x * x / ((2 * n) * (2 * n + 1)); s += t; } return s; }
constexpr double cos_s(double x) { double t = 1, s = 1; for (int n = 1; n < 12; n++) { t *= -x * x / ((2 * n - 1) * (2 * n)); s += t; } return s; }
constexpr double cos2048(int m) {
  m &= 2047; if (m > 1024) m = 2048 - m;
  bool neg = false; if (m > 512) { m = 1024 - m; neg = true; }
  double v = (m <= 256) ? cos_s(2 * PI * m / 2048) : sin_s(2 * PI * (512 - m) / 2048);
  return neg ? -v : v;
}
constexpr uint16_t to_bf16(double v) {
  if (v == 0) return 0;
  uint16_t s = 0; if (v < 0) { s = 0x8000; v = -v; }
  int e = 0; while (v >= 2) { v /= 2; e++; } while (v < 1) { v *= 2; e--; }
  double m = (v - 1) * 128; int mi = (int)m; double fr = m - mi;
  if (fr > 0.5 || (fr == 0.5 && (mi & 1))) mi++;
  if (mi == 128) { mi = 0; e++; }
  return (uint16_t)(s | ((e + 127) << 7) | mi);
}
struct CosT { uint16_t v[2048]; constexpr CosT() : v() { for (int i = 0; i < 2048; i++) v[i] = to_bf16(cos2048(i)); } };
struct alignas(1024) FT {
  uint16_t v[512 * 512];
  constexpr FT() : v() {
    CosT c;
    for (int r = 0; r < 512; r++) {
      int k = (r >> 4) * 8 + (r & 7), e = (r >> 3) & 1;
      int mul = 4 * k, add = e ? 512 : 0;
      if (k == 0 && e == 1) { mul = 1024; add = 0; }
      for (int d = 0; d < 512; d++) v[r * 512 + d] = c.v[(d * mul + add) & 2047];
    }
  }
};
struct alignas(1024) ET {
  uint16_t v[2048 * 128];
  constexpr ET() : v() {
    CosT c;
    for (int s = 0; s < 2048; s++)
      for (int j = 0; j < 64; j++) { v[s * 128 + j] = c.v[(s * j) & 2047]; v[s * 128 + 64 + j] = c.v[(s * j + 512) & 2047]; }
  }
};
struct alignas(1024) DT {
  uint16_t v[64 * 64];
  constexpr DT() : v() {
    CosT c;
    for (int r = 0; r < 64; r++)
      for (int n = 0; n < 64; n++) {
        const int sg = r >> 1, s0 = (sg & ~6) | ((sg & 2) << 1) | ((sg & 4) >> 1), e = r & 1, f = n & 1;
        const int m = 64 * s0 * (n >> 1) + (e == f ? 0 : e ? -512 : 512);
        v[r * 64 + (((n >> 3) ^ (r & 7)) << 3) + (n & 7)] = c.v[m & 2047];
      }
  }
};
}

__device__ constexpr tbl::FT g_FT = tbl::FT();
__device__ constexpr tbl::ET g_ET = tbl::ET();
__device__ constexpr tbl::DT g_DT = tbl::DT();

__device__ __align__(1024) uint16_t g_X[129 * 8192];
__device__ __align__(1024) uint16_t g_T[32 * 64 * 512];
__device__ __align__(1024) uint2 g_Ts[32 * 64];
__device__ __align__(1024) uint4 g_part[128 * 3 * 1024];
__device__ __align__(16) float g_gate[16 * 128];
__device__ __align__(16) uint2 g_Wh[2 * 2048];
__device__ unsigned g_epoch[132 * 8];
__device__ unsigned g_cntX[8 * 32], g_cntT[8 * 32], g_cntP[128 * 32], g_cntW[32], g_cntH[32];
#define PROF_EV(i) do {} while (0)
#define PROF_CK(i) do {} while (0)

__device__ __forceinline__ uint32_t smem_u32(const void* p) { return (uint32_t)__cvta_generic_to_shared(p); }
__device__ __forceinline__ void mbar_init(uint32_t bar, uint32_t cnt) { asm volatile("mbarrier.init.shared::cta.b64 [%0], %1;" ::"r"(bar), "r"(cnt)); }
__device__ __forceinline__ void mbar_expect_tx(uint32_t bar, uint32_t bytes) { asm volatile("mbarrier.arrive.expect_tx.shared::cta.b64 _, [%0], %1;" ::"r"(bar), "r"(bytes) : "memory"); }
__device__ __forceinline__ void mbar_arrive(uint32_t bar) { asm volatile("mbarrier.arrive.shared::cta.b64 _, [%0];" ::"r"(bar) : "memory"); }
__device__ __forceinline__ void mbar_wait(uint32_t bar, uint32_t parity) {
  asm volatile(
      "{\n.reg .pred p;\n.reg .u32 n;\nmov.u32 n, 0;\n"
      "W_LOOP:\nmbarrier.try_wait.parity.shared::cta.b64 p, [%0], %1;\n@p bra W_DONE;\n"
      "add.u32 n, n, 1;\nsetp.lt.u32 p, n, 0x40000;\n@p bra W_LOOP;\ntrap;\nW_DONE:\n}" ::"r"(bar), "r"(parity) : "memory");
}
__device__ __forceinline__ void bulk_load(uint32_t dst, const void* src, uint32_t bytes, uint32_t bar) {
  asm volatile("cp.async.bulk.shared::cluster.global.mbarrier::complete_tx::bytes [%0], [%1], %2, [%3];" ::"r"(dst), "l"(src), "r"(bytes), "r"(bar) : "memory");
}
__device__ __forceinline__ void cp16(uint32_t dst, const void* src) { asm volatile("cp.async.cg.shared.global [%0], [%1], 16;" ::"r"(dst), "l"(src) : "memory"); }
__device__ __forceinline__ void spin_guard(uint32_t t0) { if ((uint32_t)clock() - t0 > (1u << 30)) __trap(); }
__device__ __forceinline__ float tagf(float v, uint32_t tag) { return __uint_as_float((__float_as_uint(v) & ~1u) | tag); }
__device__ __forceinline__ float untag(float v) { return __uint_as_float(__float_as_uint(v) & ~1u); }
__device__ __forceinline__ void st_x2(float2* p, float a, float b) { asm volatile("st.relaxed.gpu.global.v2.f32 [%0], {%1,%2};" ::"l"(p), "f"(a), "f"(b) : "memory"); }
__device__ __forceinline__ float2 ld_x2(const float2* p) { float2 v; asm volatile("ld.relaxed.gpu.global.v2.f32 {%0,%1}, [%2];" : "=f"(v.x), "=f"(v.y) : "l"(p) : "memory"); return v; }
__device__ __forceinline__ void st_u2(uint2* p, uint32_t a, uint32_t b) { asm volatile("st.relaxed.gpu.global.v2.u32 [%0], {%1,%2};" ::"l"(p), "r"(a), "r"(b) : "memory"); }
__device__ __forceinline__ void prefetch2d(const CUtensorMap* m, int c0, int c1) { asm volatile("cp.async.bulk.prefetch.tensor.2d.L2.global [%0, {%1, %2}];" ::"l"(m), "r"(c0), "r"(c1) : "memory"); }
__device__ __forceinline__ void prefetch1d(const void* p, uint32_t bytes) { asm volatile("cp.async.bulk.prefetch.L2.global [%0], %1;" ::"l"(p), "r"(bytes) : "memory"); }
__device__ __forceinline__ uint32_t ld_x1(const void* p) { uint32_t v; asm volatile("ld.relaxed.gpu.global.u32 %0, [%1];" : "=r"(v) : "l"(p) : "memory"); return v; }
__device__ __forceinline__ uint4 ld_x4(const void* p) { uint4 v; asm volatile("ld.relaxed.gpu.global.v4.u32 {%0,%1,%2,%3}, [%4];" : "=r"(v.x), "=r"(v.y), "=r"(v.z), "=r"(v.w) : "l"(p) : "memory"); return v; }
__device__ __forceinline__ void st_x4(void* p, uint32_t a, uint32_t b, uint32_t c, uint32_t d) { asm volatile("st.relaxed.gpu.global.v4.u32 [%0], {%1,%2,%3,%4};" ::"l"(p), "r"(a), "r"(b), "r"(c), "r"(d) : "memory"); }
__device__ __forceinline__ uint32_t mapa(uint32_t a, uint32_t cta) { uint32_t r; asm volatile("mapa.shared::cluster.u32 %0, %1, %2;" : "=r"(r) : "r"(a), "r"(cta)); return r; }
__device__ __forceinline__ void stsm4t(uint32_t a, uint32_t r0, uint32_t r1, uint32_t r2, uint32_t r3) {
  asm volatile("stmatrix.sync.aligned.m8n8.x4.trans.shared.b16 [%0], {%1,%2,%3,%4};" ::"r"(a), "r"(r0), "r"(r1), "r"(r2), "r"(r3) : "memory");
}
__device__ __forceinline__ void hint_add(unsigned* p) { asm volatile("red.relaxed.gpu.global.add.u32 [%0], 1;" ::"l"(p) : "memory"); }
__device__ __forceinline__ void hint_wait(const unsigned* p, unsigned target) {
  const uint32_t t0 = (uint32_t)clock();
  while ((int)(ld_x1(p) - target) < 0) spin_guard(t0);
}
__device__ __forceinline__ void bulk_done_signal(unsigned* p) {
  asm volatile("cp.async.bulk.commit_group;\ncp.async.bulk.wait_group 0;\nfence.proxy.async.global;" ::: "memory");
  hint_add(p);
}
__device__ __forceinline__ void flag_wait(const unsigned* p, unsigned target) {
  hint_wait(p, target);
  asm volatile("fence.proxy.async.global;" ::: "memory");
}
__device__ __forceinline__ void tma2d(uint32_t dst, const CUtensorMap* m, uint32_t bar, int c0, int c1) {
  asm volatile("cp.async.bulk.tensor.2d.shared::cluster.global.mbarrier::complete_tx::bytes [%0], [%1, {%3, %4}], [%2];" ::"r"(dst), "l"(m), "r"(bar), "r"(c0), "r"(c1) : "memory");
}
__device__ __forceinline__ void tma3d(uint32_t dst, const CUtensorMap* m, uint32_t bar, int c0, int c1, int c2) {
  asm volatile("cp.async.bulk.tensor.3d.shared::cluster.global.mbarrier::complete_tx::bytes [%0], [%1, {%3, %4, %5}], [%2];" ::"r"(dst), "l"(m), "r"(bar), "r"(c0), "r"(c1), "r"(c2) : "memory");
}
__device__ __forceinline__ void tma4d(uint32_t dst, const CUtensorMap* m, uint32_t bar, int c0, int c1, int c2, int c3) {
  asm volatile("cp.async.bulk.tensor.4d.shared::cluster.global.mbarrier::complete_tx::bytes [%0], [%1, {%3, %4, %5, %6}], [%2];" ::"r"(dst), "l"(m), "r"(bar), "r"(c0), "r"(c1), "r"(c2), "r"(c3) : "memory");
}
__device__ __forceinline__ void wg_fence() { asm volatile("wgmma.fence.sync.aligned;" ::: "memory"); }
__device__ __forceinline__ void wg_commit() { asm volatile("wgmma.commit_group.sync.aligned;" ::: "memory"); }
template <int N> __device__ __forceinline__ void wg_wait() { asm volatile("wgmma.wait_group.sync.aligned %0;" ::"n"(N) : "memory"); }
template <int O, int N, int NN> __device__ __forceinline__ void fence_regs(float (&d)[NN]) {
#pragma unroll
  for (int i = 0; i < N; i++) asm volatile("" : "+f"(d[O + i])::"memory");
}
__device__ __forceinline__ uint32_t pack_bf16(float lo, float hi) {
  uint32_t r; asm("cvt.rn.bf16x2.f32 %0, %1, %2;" : "=r"(r) : "f"(hi), "f"(lo)); return r;
}
__device__ __forceinline__ uint32_t pack_pin(float lo, float hi) {
  uint32_t r; asm volatile("cvt.rn.bf16x2.f32 %0, %1, %2;" : "=r"(r) : "f"(hi), "f"(lo) : "memory"); return r;
}
__device__ __forceinline__ float bf_lo(uint32_t u) { return __uint_as_float(u << 16); }
__device__ __forceinline__ float bf_hi(uint32_t u) { return __uint_as_float(u & 0xffff0000u); }

__device__ __forceinline__ uint64_t d128(uint32_t lo) { uint64_t d; asm("mov.b64 %0, {%1, 0x40000040};" : "=l"(d) : "r"(lo)); return d; }
__device__ __forceinline__ uint64_t d64(uint32_t lo) { uint64_t d; asm("mov.b64 %0, {%1, 0x80000020};" : "=l"(d) : "r"(lo)); return d; }
template<int O,int TB,int ACC,int NN> __device__ __forceinline__ void mma_ss64(float (&d)[NN], uint64_t da, uint64_t db, int sd = 0){
  if constexpr (ACC == 1) asm volatile("wgmma.mma_async.sync.aligned.m64n64k16.f32.bf16.bf16 {%0,%1,%2,%3,%4,%5,%6,%7,%8,%9,%10,%11,%12,%13,%14,%15,%16,%17,%18,%19,%20,%21,%22,%23,%24,%25,%26,%27,%28,%29,%30,%31}, %32, %33, 1, 1, 1, %35, %34;"
   : "+f"(d[O+0]), "+f"(d[O+1]), "+f"(d[O+2]), "+f"(d[O+3]), "+f"(d[O+4]), "+f"(d[O+5]), "+f"(d[O+6]), "+f"(d[O+7]), "+f"(d[O+8]), "+f"(d[O+9]), "+f"(d[O+10]), "+f"(d[O+11]), "+f"(d[O+12]), "+f"(d[O+13]), "+f"(d[O+14]), "+f"(d[O+15]), "+f"(d[O+16]), "+f"(d[O+17]), "+f"(d[O+18]), "+f"(d[O+19]), "+f"(d[O+20]), "+f"(d[O+21]), "+f"(d[O+22]), "+f"(d[O+23]), "+f"(d[O+24]), "+f"(d[O+25]), "+f"(d[O+26]), "+f"(d[O+27]), "+f"(d[O+28]), "+f"(d[O+29]), "+f"(d[O+30]), "+f"(d[O+31])
   : "l"(da), "l"(db), "n"(TB & 1), "n"(TB >> 1));
  else if constexpr (ACC == 0) asm volatile("wgmma.mma_async.sync.aligned.m64n64k16.f32.bf16.bf16 {%0,%1,%2,%3,%4,%5,%6,%7,%8,%9,%10,%11,%12,%13,%14,%15,%16,%17,%18,%19,%20,%21,%22,%23,%24,%25,%26,%27,%28,%29,%30,%31}, %32, %33, 0, 1, 1, %35, %34;"
   : "=f"(d[O+0]), "=f"(d[O+1]), "=f"(d[O+2]), "=f"(d[O+3]), "=f"(d[O+4]), "=f"(d[O+5]), "=f"(d[O+6]), "=f"(d[O+7]), "=f"(d[O+8]), "=f"(d[O+9]), "=f"(d[O+10]), "=f"(d[O+11]), "=f"(d[O+12]), "=f"(d[O+13]), "=f"(d[O+14]), "=f"(d[O+15]), "=f"(d[O+16]), "=f"(d[O+17]), "=f"(d[O+18]), "=f"(d[O+19]), "=f"(d[O+20]), "=f"(d[O+21]), "=f"(d[O+22]), "=f"(d[O+23]), "=f"(d[O+24]), "=f"(d[O+25]), "=f"(d[O+26]), "=f"(d[O+27]), "=f"(d[O+28]), "=f"(d[O+29]), "=f"(d[O+30]), "=f"(d[O+31])
   : "l"(da), "l"(db), "n"(TB & 1), "n"(TB >> 1));
  else asm volatile("{\n.reg .pred p;\nsetp.ne.b32 p, %36, 0;\nwgmma.mma_async.sync.aligned.m64n64k16.f32.bf16.bf16 {%0,%1,%2,%3,%4,%5,%6,%7,%8,%9,%10,%11,%12,%13,%14,%15,%16,%17,%18,%19,%20,%21,%22,%23,%24,%25,%26,%27,%28,%29,%30,%31}, %32, %33, p, 1, 1, %35, %34;\n}"
   : "+f"(d[O+0]), "+f"(d[O+1]), "+f"(d[O+2]), "+f"(d[O+3]), "+f"(d[O+4]), "+f"(d[O+5]), "+f"(d[O+6]), "+f"(d[O+7]), "+f"(d[O+8]), "+f"(d[O+9]), "+f"(d[O+10]), "+f"(d[O+11]), "+f"(d[O+12]), "+f"(d[O+13]), "+f"(d[O+14]), "+f"(d[O+15]), "+f"(d[O+16]), "+f"(d[O+17]), "+f"(d[O+18]), "+f"(d[O+19]), "+f"(d[O+20]), "+f"(d[O+21]), "+f"(d[O+22]), "+f"(d[O+23]), "+f"(d[O+24]), "+f"(d[O+25]), "+f"(d[O+26]), "+f"(d[O+27]), "+f"(d[O+28]), "+f"(d[O+29]), "+f"(d[O+30]), "+f"(d[O+31])
   : "l"(da), "l"(db), "n"(TB & 1), "n"(TB >> 1), "r"(sd));
}
template<int O,int TB,int ACC,int NN> __device__ __forceinline__ void mma_rs64(float (&d)[NN], uint32_t a0, uint32_t a1, uint32_t a2, uint32_t a3, uint64_t db, int sd = 0){
  if constexpr (ACC == 1) asm volatile("wgmma.mma_async.sync.aligned.m64n64k16.f32.bf16.bf16 {%0,%1,%2,%3,%4,%5,%6,%7,%8,%9,%10,%11,%12,%13,%14,%15,%16,%17,%18,%19,%20,%21,%22,%23,%24,%25,%26,%27,%28,%29,%30,%31}, {%32,%33,%34,%35}, %36, 1, 1, 1, %37;"
   : "+f"(d[O+0]), "+f"(d[O+1]), "+f"(d[O+2]), "+f"(d[O+3]), "+f"(d[O+4]), "+f"(d[O+5]), "+f"(d[O+6]), "+f"(d[O+7]), "+f"(d[O+8]), "+f"(d[O+9]), "+f"(d[O+10]), "+f"(d[O+11]), "+f"(d[O+12]), "+f"(d[O+13]), "+f"(d[O+14]), "+f"(d[O+15]), "+f"(d[O+16]), "+f"(d[O+17]), "+f"(d[O+18]), "+f"(d[O+19]), "+f"(d[O+20]), "+f"(d[O+21]), "+f"(d[O+22]), "+f"(d[O+23]), "+f"(d[O+24]), "+f"(d[O+25]), "+f"(d[O+26]), "+f"(d[O+27]), "+f"(d[O+28]), "+f"(d[O+29]), "+f"(d[O+30]), "+f"(d[O+31])
   : "r"(a0), "r"(a1), "r"(a2), "r"(a3), "l"(db), "n"(TB));
  else if constexpr (ACC == 0) asm volatile("wgmma.mma_async.sync.aligned.m64n64k16.f32.bf16.bf16 {%0,%1,%2,%3,%4,%5,%6,%7,%8,%9,%10,%11,%12,%13,%14,%15,%16,%17,%18,%19,%20,%21,%22,%23,%24,%25,%26,%27,%28,%29,%30,%31}, {%32,%33,%34,%35}, %36, 0, 1, 1, %37;"
   : "=f"(d[O+0]), "=f"(d[O+1]), "=f"(d[O+2]), "=f"(d[O+3]), "=f"(d[O+4]), "=f"(d[O+5]), "=f"(d[O+6]), "=f"(d[O+7]), "=f"(d[O+8]), "=f"(d[O+9]), "=f"(d[O+10]), "=f"(d[O+11]), "=f"(d[O+12]), "=f"(d[O+13]), "=f"(d[O+14]), "=f"(d[O+15]), "=f"(d[O+16]), "=f"(d[O+17]), "=f"(d[O+18]), "=f"(d[O+19]), "=f"(d[O+20]), "=f"(d[O+21]), "=f"(d[O+22]), "=f"(d[O+23]), "=f"(d[O+24]), "=f"(d[O+25]), "=f"(d[O+26]), "=f"(d[O+27]), "=f"(d[O+28]), "=f"(d[O+29]), "=f"(d[O+30]), "=f"(d[O+31])
   : "r"(a0), "r"(a1), "r"(a2), "r"(a3), "l"(db), "n"(TB));
  else asm volatile("{\n.reg .pred p;\nsetp.ne.b32 p, %38, 0;\nwgmma.mma_async.sync.aligned.m64n64k16.f32.bf16.bf16 {%0,%1,%2,%3,%4,%5,%6,%7,%8,%9,%10,%11,%12,%13,%14,%15,%16,%17,%18,%19,%20,%21,%22,%23,%24,%25,%26,%27,%28,%29,%30,%31}, {%32,%33,%34,%35}, %36, p, 1, 1, %37;\n}"
   : "+f"(d[O+0]), "+f"(d[O+1]), "+f"(d[O+2]), "+f"(d[O+3]), "+f"(d[O+4]), "+f"(d[O+5]), "+f"(d[O+6]), "+f"(d[O+7]), "+f"(d[O+8]), "+f"(d[O+9]), "+f"(d[O+10]), "+f"(d[O+11]), "+f"(d[O+12]), "+f"(d[O+13]), "+f"(d[O+14]), "+f"(d[O+15]), "+f"(d[O+16]), "+f"(d[O+17]), "+f"(d[O+18]), "+f"(d[O+19]), "+f"(d[O+20]), "+f"(d[O+21]), "+f"(d[O+22]), "+f"(d[O+23]), "+f"(d[O+24]), "+f"(d[O+25]), "+f"(d[O+26]), "+f"(d[O+27]), "+f"(d[O+28]), "+f"(d[O+29]), "+f"(d[O+30]), "+f"(d[O+31])
   : "r"(a0), "r"(a1), "r"(a2), "r"(a3), "l"(db), "n"(TB), "r"(sd));
}
template<int O,int TB,int ACC,int NN> __device__ __forceinline__ void mma_ss128(float (&d)[NN], uint64_t da, uint64_t db, int sd = 0){
  if constexpr (ACC == 1) asm volatile("wgmma.mma_async.sync.aligned.m64n128k16.f32.bf16.bf16 {%0,%1,%2,%3,%4,%5,%6,%7,%8,%9,%10,%11,%12,%13,%14,%15,%16,%17,%18,%19,%20,%21,%22,%23,%24,%25,%26,%27,%28,%29,%30,%31,%32,%33,%34,%35,%36,%37,%38,%39,%40,%41,%42,%43,%44,%45,%46,%47,%48,%49,%50,%51,%52,%53,%54,%55,%56,%57,%58,%59,%60,%61,%62,%63}, %64, %65, 1, 1, 1, %67, %66;"
   : "+f"(d[O+0]), "+f"(d[O+1]), "+f"(d[O+2]), "+f"(d[O+3]), "+f"(d[O+4]), "+f"(d[O+5]), "+f"(d[O+6]), "+f"(d[O+7]), "+f"(d[O+8]), "+f"(d[O+9]), "+f"(d[O+10]), "+f"(d[O+11]), "+f"(d[O+12]), "+f"(d[O+13]), "+f"(d[O+14]), "+f"(d[O+15]), "+f"(d[O+16]), "+f"(d[O+17]), "+f"(d[O+18]), "+f"(d[O+19]), "+f"(d[O+20]), "+f"(d[O+21]), "+f"(d[O+22]), "+f"(d[O+23]), "+f"(d[O+24]), "+f"(d[O+25]), "+f"(d[O+26]), "+f"(d[O+27]), "+f"(d[O+28]), "+f"(d[O+29]), "+f"(d[O+30]), "+f"(d[O+31]), "+f"(d[O+32]), "+f"(d[O+33]), "+f"(d[O+34]), "+f"(d[O+35]), "+f"(d[O+36]), "+f"(d[O+37]), "+f"(d[O+38]), "+f"(d[O+39]), "+f"(d[O+40]), "+f"(d[O+41]), "+f"(d[O+42]), "+f"(d[O+43]), "+f"(d[O+44]), "+f"(d[O+45]), "+f"(d[O+46]), "+f"(d[O+47]), "+f"(d[O+48]), "+f"(d[O+49]), "+f"(d[O+50]), "+f"(d[O+51]), "+f"(d[O+52]), "+f"(d[O+53]), "+f"(d[O+54]), "+f"(d[O+55]), "+f"(d[O+56]), "+f"(d[O+57]), "+f"(d[O+58]), "+f"(d[O+59]), "+f"(d[O+60]), "+f"(d[O+61]), "+f"(d[O+62]), "+f"(d[O+63])
   : "l"(da), "l"(db), "n"(TB & 1), "n"(TB >> 1));
  else if constexpr (ACC == 0) asm volatile("wgmma.mma_async.sync.aligned.m64n128k16.f32.bf16.bf16 {%0,%1,%2,%3,%4,%5,%6,%7,%8,%9,%10,%11,%12,%13,%14,%15,%16,%17,%18,%19,%20,%21,%22,%23,%24,%25,%26,%27,%28,%29,%30,%31,%32,%33,%34,%35,%36,%37,%38,%39,%40,%41,%42,%43,%44,%45,%46,%47,%48,%49,%50,%51,%52,%53,%54,%55,%56,%57,%58,%59,%60,%61,%62,%63}, %64, %65, 0, 1, 1, %67, %66;"
   : "=f"(d[O+0]), "=f"(d[O+1]), "=f"(d[O+2]), "=f"(d[O+3]), "=f"(d[O+4]), "=f"(d[O+5]), "=f"(d[O+6]), "=f"(d[O+7]), "=f"(d[O+8]), "=f"(d[O+9]), "=f"(d[O+10]), "=f"(d[O+11]), "=f"(d[O+12]), "=f"(d[O+13]), "=f"(d[O+14]), "=f"(d[O+15]), "=f"(d[O+16]), "=f"(d[O+17]), "=f"(d[O+18]), "=f"(d[O+19]), "=f"(d[O+20]), "=f"(d[O+21]), "=f"(d[O+22]), "=f"(d[O+23]), "=f"(d[O+24]), "=f"(d[O+25]), "=f"(d[O+26]), "=f"(d[O+27]), "=f"(d[O+28]), "=f"(d[O+29]), "=f"(d[O+30]), "=f"(d[O+31]), "=f"(d[O+32]), "=f"(d[O+33]), "=f"(d[O+34]), "=f"(d[O+35]), "=f"(d[O+36]), "=f"(d[O+37]), "=f"(d[O+38]), "=f"(d[O+39]), "=f"(d[O+40]), "=f"(d[O+41]), "=f"(d[O+42]), "=f"(d[O+43]), "=f"(d[O+44]), "=f"(d[O+45]), "=f"(d[O+46]), "=f"(d[O+47]), "=f"(d[O+48]), "=f"(d[O+49]), "=f"(d[O+50]), "=f"(d[O+51]), "=f"(d[O+52]), "=f"(d[O+53]), "=f"(d[O+54]), "=f"(d[O+55]), "=f"(d[O+56]), "=f"(d[O+57]), "=f"(d[O+58]), "=f"(d[O+59]), "=f"(d[O+60]), "=f"(d[O+61]), "=f"(d[O+62]), "=f"(d[O+63])
   : "l"(da), "l"(db), "n"(TB & 1), "n"(TB >> 1));
  else asm volatile("{\n.reg .pred p;\nsetp.ne.b32 p, %68, 0;\nwgmma.mma_async.sync.aligned.m64n128k16.f32.bf16.bf16 {%0,%1,%2,%3,%4,%5,%6,%7,%8,%9,%10,%11,%12,%13,%14,%15,%16,%17,%18,%19,%20,%21,%22,%23,%24,%25,%26,%27,%28,%29,%30,%31,%32,%33,%34,%35,%36,%37,%38,%39,%40,%41,%42,%43,%44,%45,%46,%47,%48,%49,%50,%51,%52,%53,%54,%55,%56,%57,%58,%59,%60,%61,%62,%63}, %64, %65, p, 1, 1, %67, %66;\n}"
   : "+f"(d[O+0]), "+f"(d[O+1]), "+f"(d[O+2]), "+f"(d[O+3]), "+f"(d[O+4]), "+f"(d[O+5]), "+f"(d[O+6]), "+f"(d[O+7]), "+f"(d[O+8]), "+f"(d[O+9]), "+f"(d[O+10]), "+f"(d[O+11]), "+f"(d[O+12]), "+f"(d[O+13]), "+f"(d[O+14]), "+f"(d[O+15]), "+f"(d[O+16]), "+f"(d[O+17]), "+f"(d[O+18]), "+f"(d[O+19]), "+f"(d[O+20]), "+f"(d[O+21]), "+f"(d[O+22]), "+f"(d[O+23]), "+f"(d[O+24]), "+f"(d[O+25]), "+f"(d[O+26]), "+f"(d[O+27]), "+f"(d[O+28]), "+f"(d[O+29]), "+f"(d[O+30]), "+f"(d[O+31]), "+f"(d[O+32]), "+f"(d[O+33]), "+f"(d[O+34]), "+f"(d[O+35]), "+f"(d[O+36]), "+f"(d[O+37]), "+f"(d[O+38]), "+f"(d[O+39]), "+f"(d[O+40]), "+f"(d[O+41]), "+f"(d[O+42]), "+f"(d[O+43]), "+f"(d[O+44]), "+f"(d[O+45]), "+f"(d[O+46]), "+f"(d[O+47]), "+f"(d[O+48]), "+f"(d[O+49]), "+f"(d[O+50]), "+f"(d[O+51]), "+f"(d[O+52]), "+f"(d[O+53]), "+f"(d[O+54]), "+f"(d[O+55]), "+f"(d[O+56]), "+f"(d[O+57]), "+f"(d[O+58]), "+f"(d[O+59]), "+f"(d[O+60]), "+f"(d[O+61]), "+f"(d[O+62]), "+f"(d[O+63])
   : "l"(da), "l"(db), "n"(TB & 1), "n"(TB >> 1), "r"(sd));
}
template<int O,int TB,int ACC,int NN> __device__ __forceinline__ void mma_rs128(float (&d)[NN], uint32_t a0, uint32_t a1, uint32_t a2, uint32_t a3, uint64_t db, int sd = 0){
  if constexpr (ACC == 1) asm volatile("wgmma.mma_async.sync.aligned.m64n128k16.f32.bf16.bf16 {%0,%1,%2,%3,%4,%5,%6,%7,%8,%9,%10,%11,%12,%13,%14,%15,%16,%17,%18,%19,%20,%21,%22,%23,%24,%25,%26,%27,%28,%29,%30,%31,%32,%33,%34,%35,%36,%37,%38,%39,%40,%41,%42,%43,%44,%45,%46,%47,%48,%49,%50,%51,%52,%53,%54,%55,%56,%57,%58,%59,%60,%61,%62,%63}, {%64,%65,%66,%67}, %68, 1, 1, 1, %69;"
   : "+f"(d[O+0]), "+f"(d[O+1]), "+f"(d[O+2]), "+f"(d[O+3]), "+f"(d[O+4]), "+f"(d[O+5]), "+f"(d[O+6]), "+f"(d[O+7]), "+f"(d[O+8]), "+f"(d[O+9]), "+f"(d[O+10]), "+f"(d[O+11]), "+f"(d[O+12]), "+f"(d[O+13]), "+f"(d[O+14]), "+f"(d[O+15]), "+f"(d[O+16]), "+f"(d[O+17]), "+f"(d[O+18]), "+f"(d[O+19]), "+f"(d[O+20]), "+f"(d[O+21]), "+f"(d[O+22]), "+f"(d[O+23]), "+f"(d[O+24]), "+f"(d[O+25]), "+f"(d[O+26]), "+f"(d[O+27]), "+f"(d[O+28]), "+f"(d[O+29]), "+f"(d[O+30]), "+f"(d[O+31]), "+f"(d[O+32]), "+f"(d[O+33]), "+f"(d[O+34]), "+f"(d[O+35]), "+f"(d[O+36]), "+f"(d[O+37]), "+f"(d[O+38]), "+f"(d[O+39]), "+f"(d[O+40]), "+f"(d[O+41]), "+f"(d[O+42]), "+f"(d[O+43]), "+f"(d[O+44]), "+f"(d[O+45]), "+f"(d[O+46]), "+f"(d[O+47]), "+f"(d[O+48]), "+f"(d[O+49]), "+f"(d[O+50]), "+f"(d[O+51]), "+f"(d[O+52]), "+f"(d[O+53]), "+f"(d[O+54]), "+f"(d[O+55]), "+f"(d[O+56]), "+f"(d[O+57]), "+f"(d[O+58]), "+f"(d[O+59]), "+f"(d[O+60]), "+f"(d[O+61]), "+f"(d[O+62]), "+f"(d[O+63])
   : "r"(a0), "r"(a1), "r"(a2), "r"(a3), "l"(db), "n"(TB));
  else if constexpr (ACC == 0) asm volatile("wgmma.mma_async.sync.aligned.m64n128k16.f32.bf16.bf16 {%0,%1,%2,%3,%4,%5,%6,%7,%8,%9,%10,%11,%12,%13,%14,%15,%16,%17,%18,%19,%20,%21,%22,%23,%24,%25,%26,%27,%28,%29,%30,%31,%32,%33,%34,%35,%36,%37,%38,%39,%40,%41,%42,%43,%44,%45,%46,%47,%48,%49,%50,%51,%52,%53,%54,%55,%56,%57,%58,%59,%60,%61,%62,%63}, {%64,%65,%66,%67}, %68, 0, 1, 1, %69;"
   : "=f"(d[O+0]), "=f"(d[O+1]), "=f"(d[O+2]), "=f"(d[O+3]), "=f"(d[O+4]), "=f"(d[O+5]), "=f"(d[O+6]), "=f"(d[O+7]), "=f"(d[O+8]), "=f"(d[O+9]), "=f"(d[O+10]), "=f"(d[O+11]), "=f"(d[O+12]), "=f"(d[O+13]), "=f"(d[O+14]), "=f"(d[O+15]), "=f"(d[O+16]), "=f"(d[O+17]), "=f"(d[O+18]), "=f"(d[O+19]), "=f"(d[O+20]), "=f"(d[O+21]), "=f"(d[O+22]), "=f"(d[O+23]), "=f"(d[O+24]), "=f"(d[O+25]), "=f"(d[O+26]), "=f"(d[O+27]), "=f"(d[O+28]), "=f"(d[O+29]), "=f"(d[O+30]), "=f"(d[O+31]), "=f"(d[O+32]), "=f"(d[O+33]), "=f"(d[O+34]), "=f"(d[O+35]), "=f"(d[O+36]), "=f"(d[O+37]), "=f"(d[O+38]), "=f"(d[O+39]), "=f"(d[O+40]), "=f"(d[O+41]), "=f"(d[O+42]), "=f"(d[O+43]), "=f"(d[O+44]), "=f"(d[O+45]), "=f"(d[O+46]), "=f"(d[O+47]), "=f"(d[O+48]), "=f"(d[O+49]), "=f"(d[O+50]), "=f"(d[O+51]), "=f"(d[O+52]), "=f"(d[O+53]), "=f"(d[O+54]), "=f"(d[O+55]), "=f"(d[O+56]), "=f"(d[O+57]), "=f"(d[O+58]), "=f"(d[O+59]), "=f"(d[O+60]), "=f"(d[O+61]), "=f"(d[O+62]), "=f"(d[O+63])
   : "r"(a0), "r"(a1), "r"(a2), "r"(a3), "l"(db), "n"(TB));
  else asm volatile("{\n.reg .pred p;\nsetp.ne.b32 p, %70, 0;\nwgmma.mma_async.sync.aligned.m64n128k16.f32.bf16.bf16 {%0,%1,%2,%3,%4,%5,%6,%7,%8,%9,%10,%11,%12,%13,%14,%15,%16,%17,%18,%19,%20,%21,%22,%23,%24,%25,%26,%27,%28,%29,%30,%31,%32,%33,%34,%35,%36,%37,%38,%39,%40,%41,%42,%43,%44,%45,%46,%47,%48,%49,%50,%51,%52,%53,%54,%55,%56,%57,%58,%59,%60,%61,%62,%63}, {%64,%65,%66,%67}, %68, p, 1, 1, %69;\n}"
   : "+f"(d[O+0]), "+f"(d[O+1]), "+f"(d[O+2]), "+f"(d[O+3]), "+f"(d[O+4]), "+f"(d[O+5]), "+f"(d[O+6]), "+f"(d[O+7]), "+f"(d[O+8]), "+f"(d[O+9]), "+f"(d[O+10]), "+f"(d[O+11]), "+f"(d[O+12]), "+f"(d[O+13]), "+f"(d[O+14]), "+f"(d[O+15]), "+f"(d[O+16]), "+f"(d[O+17]), "+f"(d[O+18]), "+f"(d[O+19]), "+f"(d[O+20]), "+f"(d[O+21]), "+f"(d[O+22]), "+f"(d[O+23]), "+f"(d[O+24]), "+f"(d[O+25]), "+f"(d[O+26]), "+f"(d[O+27]), "+f"(d[O+28]), "+f"(d[O+29]), "+f"(d[O+30]), "+f"(d[O+31]), "+f"(d[O+32]), "+f"(d[O+33]), "+f"(d[O+34]), "+f"(d[O+35]), "+f"(d[O+36]), "+f"(d[O+37]), "+f"(d[O+38]), "+f"(d[O+39]), "+f"(d[O+40]), "+f"(d[O+41]), "+f"(d[O+42]), "+f"(d[O+43]), "+f"(d[O+44]), "+f"(d[O+45]), "+f"(d[O+46]), "+f"(d[O+47]), "+f"(d[O+48]), "+f"(d[O+49]), "+f"(d[O+50]), "+f"(d[O+51]), "+f"(d[O+52]), "+f"(d[O+53]), "+f"(d[O+54]), "+f"(d[O+55]), "+f"(d[O+56]), "+f"(d[O+57]), "+f"(d[O+58]), "+f"(d[O+59]), "+f"(d[O+60]), "+f"(d[O+61]), "+f"(d[O+62]), "+f"(d[O+63])
   : "r"(a0), "r"(a1), "r"(a2), "r"(a3), "l"(db), "n"(TB), "r"(sd));
}

#define NEARLY 0
#define XAHEAD 3
#define WAFTER 7
#define WPACE 100
#define GATE_AT 0
#define TPACE 40
#define PFMODE 0
#define MAPMODE 0
template <int V> struct IC { static constexpr int value = V; };
struct Maps { CUtensorMap x, ft, g32, u32, wr, wi, g64, u64, e, xs, ts, t, d192, d32; };

constexpr int NCTA = 130;
constexpr int U = 16384;
constexpr int TB = 36864;
constexpr int NR = 4;
constexpr int OFF_RING = 8 * U, OFF_Z = 9 * U, OFF_XB = 12 * U, OFF_T = 13 * U, OFF_D = OFF_T, OFF_SP = OFF_T + 12288;
constexpr int OFF_BAR = 14 * U;
constexpr int SMEM_BYTES = OFF_BAR + 512;
constexpr int B_FX = 0, B_FA = 8, B_FT = 12, B_Z = 16, B_W = 20, B_HX = 21, B_TL = 22, B_HP = 23, B_WR = 26;
constexpr int B_EA = 30, B_ET = 34, B_RDY = 38;
constexpr int B_T = 39, B_XS = 40, NBAR = 41;
__host__ __device__ constexpr int rslot(int n) { return n % NR; }
__host__ __device__ constexpr int rpar(int n) { return (n / NR) & 1; }

__global__ void __cluster_dims__(2, 1, 1) __launch_bounds__(512, 1)
fused_kernel(const __grid_constant__ Maps maps, const __nv_bfloat16* __restrict__ x, const __nv_bfloat16* __restrict__ w_r,
             const __nv_bfloat16* __restrict__ w_i, const __nv_bfloat16* __restrict__ gate_w, __nv_bfloat16* __restrict__ out) {
  extern __shared__ __align__(1024) uint8_t smem[];
  const uint32_t sb = smem_u32(smem);
  const uint32_t bars = sb + OFF_BAR;
  const int tid = threadIdx.x, lane = tid & 31;
  const int warp = __shfl_sync(0xffffffffu, tid >> 5, 0);
  const bool helper = blockIdx.x >= 128;
  const int cl = (blockIdx.x >> 1) & 63, rank = blockIdx.x & 1;
  const int q4 = cl & 3, rb = cl >> 2;
  const int j = 2 * q4 + rank;
  const int f_full = 448 * q4 + (rank ? 256 : 0);
  const int f_half = 448 * q4 + (rank ? 224 : 192);
  const int kg = 2 * j + (rb >> 3), tn = rb & 7;

  if (tid == 64) { PROF_EV(0); PROF_CK(40); }
  auto ring_part = [&](int p, int n, int slot) {
    const uint32_t fb = bars + 8 * (B_FA + slot), dst = sb + OFF_RING + slot * U;
    const bool table = n == 9 || n == 10 || n >= 34;
    const int q = n == 8 ? 0 : n - 10;
    if (p == 0) {
      mbar_expect_tx(fb, U);
      if (n < 8) tma2d(dst, &maps.ft, fb, 64 * n, 64 * j);
      else if (table) tma4d(dst, &maps.e, fb, 0, 0, 0, 2 * rb + (n >= 34 ? n - 34 : n - 9));
      else tma2d(dst, &maps.g64, fb, f_full + 64 * (q >> 3), 64 * (q & 7));
    } else if (p == 1) {
      if (n < 8) { tma2d(dst + 8192, &maps.g32, fb, f_half, 64 * n); tma2d(dst + 12288, &maps.u32, fb, f_half, 64 * n); }
      else if (!table) tma2d(dst + 8192, &maps.u64, fb, f_full + 64 * (q >> 3), 64 * (q & 7));
    }
  };
  auto x_load = [&](int q) {
    mbar_expect_tx(bars + 8 * (B_FX + q), U);
    tma3d(sb + q * U, &maps.x, bars + 8 * (B_FX + q), 64 * q, 0, 2 * rb);
  };
  if (warp >= 12) {
    if (warp < 14) {
      if (lane == 0) {
#pragma unroll
        for (int i = 0; i < 6; i++) mbar_init(bars + 8 * (2 * i + warp - 12), 1);
        asm volatile("fence.proxy.async.shared::cta;" ::: "memory");
        if (!helper) {
#pragma unroll 1
          for (int n = warp - 12; n < NR; n += 2) {
            const uint32_t fb = bars + 8 * (B_FA + n), dst = sb + OFF_RING + n * U;
            x_load(n);
            mbar_expect_tx(fb, U);
            tma2d(dst, &maps.ft, fb, 64 * n, 64 * j);
            tma2d(dst + 8192, &maps.g32, fb, f_half, 64 * n);
            tma2d(dst + 12288, &maps.u32, fb, f_half, 64 * n);
          }
        }
      }
    } else if (lane == 0) {
      if (warp == 15) {
#pragma unroll
        for (int i = B_FT; i < NBAR; i++) mbar_init(bars + 8 * i, i < B_EA ? 1 : i < B_T ? 2 : i < B_XS ? 4 : 8);
#pragma unroll
        for (int i = 0; i < 4; i++) mbar_expect_tx(bars + 8 * (B_Z + i), U);
        asm volatile("fence.mbarrier_init.release.cluster;" ::: "memory");
        asm volatile("fence.proxy.async.shared::cta;" ::: "memory");
      } else {
#pragma unroll
        for (int i = 1; i < 14; i++) asm volatile("prefetch.tensormap [%0];" ::"l"((const char*)&maps + i * 128) : "memory");
      }
    }
    __syncwarp();
    asm volatile("bar.arrive 0, 384;" ::: "memory");
    asm volatile("bar.arrive 4, 256;" ::: "memory");
    asm volatile("bar.sync 3, 128;" ::: "memory");
  }
  asm volatile("barrier.cluster.arrive.relaxed.aligned;" ::: "memory");
  if (tid == 64) PROF_EV(38);

  if (warp >= 12) {
    asm volatile("setmaxnreg.dec.sync.aligned.u32 24;");
    if (lane == 0 && (!helper || warp == 15)) {
      if (warp < 14) {
        if (warp == 12) x_load(NR);
        int slot = 0, par = 0;
#pragma unroll 1
        for (int n = NR; n < 36; n++) {
          mbar_wait(bars + 8 * (B_EA + slot), par);
          ring_part(warp - 12, n, slot);
          if (warp == 12 && n < 7) x_load(n + 1);
          if (++slot == NR) { slot = 0; par ^= 1; }
        }
      } else if (warp == 15) {
        const unsigned ep1 = ld_x1(&g_epoch[blockIdx.x * 8]) + 1;
        flag_wait(&g_cntX[helper ? 0 : 32 * j], ep1 * 16u);
        PROF_EV(22);
        mbar_expect_tx(bars + 8 * B_HX, U);
        bulk_load(sb + OFF_XB, g_X + (size_t)(helper ? 128 : kg * 8 + tn) * 8192, U, bars + 8 * B_HX);
        if (!helper) {
          flag_wait(&g_cntT[32 * j], ep1 * 16u);
          PROF_EV(23);
          mbar_expect_tx(bars + 8 * B_TL, U);
          tma3d(sb + OFF_T, &maps.t, bars + 8 * B_TL, 64 * j, 0, 2 * rb);
#pragma unroll 1
          for (int i = 0; i < 3; i++) { hint_wait(&g_cntP[32 * (rb * 8 + j) + i], ep1 * 8u); mbar_arrive(bars + 8 * (B_HP + i)); }
        }
      } else {
        mbar_wait(bars + 8 * B_XS, 0);
#pragma unroll
        for (int h2 = 0; h2 < 2; h2++) {
          const int s0 = 2 * rb + h2, sg = (s0 & ~6) | ((s0 & 2) << 1) | ((s0 & 4) >> 1);
          asm volatile("cp.async.bulk.tensor.4d.global.shared::cta.bulk_group [%0, {%2, %3, %4, %5}], [%1];" ::"l"(&maps.xs), "r"(sb + OFF_XB + h2 * 8192),
                       "r"(0), "r"(sg), "r"(0), "r"(16 * j) : "memory");
          if (j == 0) {
#pragma unroll
            for (int c = 0; c < 2; c++)
              asm volatile("cp.async.bulk.global.shared::cta.bulk_group [%0], [%1], 256;" ::"l"(g_X + 128 * 8192 + c * 4096 + sg * 128),
                           "r"(sb + OFF_SP + h2 * 512 + c * 256) : "memory");
          }
        }
        bulk_done_signal(&g_cntX[32 * j]);
        PROF_EV(20);
#pragma unroll 1
        for (int t = 0; t < 8; t++) {
          const int i = t < 3 ? t + 1 : t < 6 ? t - 2 : 0;
          const int col = 64 * (2 * ((q4 + i) & 3) + ((t < 3 || t == 6) ? 1 - rank : rank));
          const uint32_t fb = bars + 8 * (B_FT + (t & 3)), dst = sb + (t & 3) * TB;
          mbar_wait(bars + 8 * (B_ET + (t == 0 ? 1 : t & 3)), t >> 2);
          mbar_expect_tx(fb, TB);
          tma2d(dst, &maps.d192, fb, col, f_full);
          tma2d(dst + 24576, &maps.d32, fb, col, f_half);
          tma2d(dst + 28672, &maps.ft, fb, col, 64 * j);
        }
      }
    }
  } else if (warp >= 8) {
    asm volatile("setmaxnreg.dec.sync.aligned.u32 104;");
    const int t = tid - 256, w = warp - 8;
    const uint32_t ep = ld_x1(&g_epoch[blockIdx.x * 8]);
    const uint32_t tag = (ep + 1) & 1;
    auto gate_rows = [&] {
      uint4 xv[8], gv[2];
#pragma unroll
      for (int i = 0; i < 4; i++) {
        const int r = 16 * j + 4 * w + i;
        const uint4* p = (const uint4*)(x + (size_t)(2 * rb + (r >> 6) + 32 * (r & 63)) * 512) + lane;
        xv[2 * i] = __ldg(p); xv[2 * i + 1] = __ldg(p + 32);
      }
      gv[0] = __ldg((const uint4*)gate_w + lane); gv[1] = __ldg((const uint4*)gate_w + lane + 32);
      {
        float z[4];
#pragma unroll
        for (int i = 0; i < 4; i++) {
          float a = 0.f;
#pragma unroll
          for (int hh = 0; hh < 2; hh++) {
            const uint4 u = xv[2 * i + hh], v = gv[hh];
            a = fmaf(bf_lo(u.x), bf_lo(v.x), a); a = fmaf(bf_hi(u.x), bf_hi(v.x), a);
            a = fmaf(bf_lo(u.y), bf_lo(v.y), a); a = fmaf(bf_hi(u.y), bf_hi(v.y), a);
            a = fmaf(bf_lo(u.z), bf_lo(v.z), a); a = fmaf(bf_hi(u.z), bf_hi(v.z), a);
            a = fmaf(bf_lo(u.w), bf_lo(v.w), a); a = fmaf(bf_hi(u.w), bf_hi(v.w), a);
          }
#pragma unroll
          for (int o = 16; o; o >>= 1) a += __shfl_xor_sync(0xffffffffu, a, o);
          z[i] = a;
        }
        if (lane < 4) {
          const float zz = lane == 0 ? z[0] : lane == 1 ? z[1] : lane == 2 ? z[2] : z[3];
          asm volatile("st.relaxed.gpu.global.f32 [%0], %1;" ::"l"(g_gate + rb * 128 + 16 * j + 4 * w + lane), "f"(tagf(1.0f / (1.0f + __expf(-zz)), tag)) : "memory");
        }
        if (t == 0) PROF_EV(18);
      }
      if (w == 0) {
        const int c = lane >> 4, jj = 16 * blockIdx.x + (lane & 15), jm = (2048 - jj) & 2047;
        const unsigned short* pr = (const unsigned short*)w_r + 256 * c;
        const unsigned short* pi = (const unsigned short*)w_i + 256 * c;
        const float wr = 0.25f * (bf_lo(__ldg(pr + jj * 257)) + bf_lo(__ldg(pr + jm * 257)));
        const float wi = 0.25f * (bf_lo(__ldg(pi + jj * 257)) - bf_lo(__ldg(pi + jm * 257)));
        st_u2(g_Wh + c * 2048 + jj, c ? pack_bf16(-wi, wr) : pack_bf16(wr, wi), tag);
        __syncwarp();
        if (lane == 0) hint_add(&g_cntW[0]);
      }
    };
    {
      const int g = lane >> 2, q = lane & 3;
      uint32_t wf[32];
      if (!helper) {
        gate_rows();
        asm volatile("bar.sync 4, 256;" ::: "memory");
        const uint32_t wa = sb + OFF_T + w * (3072 + 4) + q * 48 + g * 2;
        mbar_wait(bars + 8 * (B_FX + WAFTER), 0);
        if (t == 0) PROF_EV(32);
        __nanosleep(WPACE * w);
#pragma unroll
        for (int ri = 0; ri < 2; ri++) {
          if (lane == 0) {
            mbar_expect_tx(bars + 8 * (B_WR + w), 3072);
            tma4d(sb + OFF_T + w * 3072, ri ? &maps.wi : &maps.wr, bars + 8 * (B_WR + w), 16 * kg, 0, 2 * w, tn);
          }
          mbar_wait(bars + 8 * (B_WR + w), ri);
#pragma unroll
          for (int n2 = 0; n2 < 4; n2++) {
            uint32_t v[8];
#pragma unroll
            for (int i = 0; i < 8; i++)
              asm volatile("ld.shared.u16 %0, [%1];" : "=r"(v[i]) : "r"(wa + (2 * n2 + ((i >> 1) & 1)) * 192 + (i & 1) * (1536 + 2) + (i >> 2) * 16) : "memory");
#pragma unroll
            for (int i = 0; i < 8; i++) {
              uint32_t& d = wf[(i >> 2) * 16 + 4 * n2 + (i & 3)];
              d = ri ? d | (v[i] << 16) : v[i];
              asm volatile("" : "+r"(d)::"memory");
            }
          }
          __syncwarp();
        }
        asm volatile("bar.sync 1, 128;" ::: "memory");
        if (t == 0) PROF_EV(11);
      } else {
        asm volatile("bar.sync 4, 256;" ::: "memory");
        hint_wait(&g_cntW[0], (ep + 1) * 128u);
        const uint32_t t0 = (uint32_t)clock();
#pragma unroll 1
        for (;;) {
          uint32_t bad = 0;
#pragma unroll
          for (int i = 0; i < 32; i++) {
            const float2 v = ld_x2((const float2*)g_Wh + (i >> 4) * 2048 + 16 * w + g + 8 * (i & 1) + 64 * q + ((i >> 1) & 7) * 256);
            wf[i] = __float_as_uint(v.x); bad |= __float_as_uint(v.y) ^ tag;
          }
          if (!__any_sync(0xffffffffu, bad & 1)) break;
          spin_guard(t0);
        }
        if (t == 0) PROF_EV(11);
      }
      if (t == 0) { mbar_expect_tx(bars + 8 * B_W, 8192); bulk_load(sb + OFF_D, g_DT.v, 8192, bars + 8 * B_W); }
      mbar_wait(bars + 8 * B_W, 0);
      mbar_wait(bars + 8 * B_HX, 0);
      if (t == 0) PROF_EV(12);
      const uint32_t dd = (sb & 0x3FFFF) >> 4;
      const uint64_t dF = d128((dd + (OFF_D >> 4)) | (512u << 16)), dI = d128((dd + (OFF_D >> 4)) | (1u << 16)), dA = d128((dd + (OFF_XB >> 4)) | (512u << 16));
      float az[32];
      const int zero = blockIdx.x >> 16;
      uint32_t pf[32];
#pragma unroll
      for (int mt = 0; mt < 2; mt++) {
        wg_fence();
        if (mt == 0) mma_ss64<0, 3, 0>(az, dA, dF);
        else mma_ss64<0, 3, 2>(az, dA + 512, dF, zero);
#pragma unroll
        for (int k = 1; k < 4; k++) mma_ss64<0, 3, 1>(az, dA + (mt * 512 + k * 128), dF + k * 128);
        wg_commit();
        wg_wait<0>();
        fence_regs<0, 32>(az);
#pragma unroll
        for (int i = 0; i < 16; i++) {
          const float wr = bf_lo(wf[16 * mt + i]), wi = bf_hi(wf[16 * mt + i]);
          pf[16 * mt + i] = pack_pin(fmaf(az[2 * i], wr, -az[2 * i + 1] * wi), fmaf(az[2 * i], wi, az[2 * i + 1] * wr));
        }
      }
      if (t == 0) PROF_EV(16);
#pragma unroll
      for (int mt = 0; mt < 2; mt++) {
        wg_fence();
        mma_rs64<0, 0, 2>(az, pf[16 * mt], pf[16 * mt + 1], pf[16 * mt + 2], pf[16 * mt + 3], dI, mt ? (int)helper : zero);
#pragma unroll
        for (int k = 1; k < 4; k++) mma_rs64<0, 0, 1>(az, pf[16 * mt + 4 * k], pf[16 * mt + 4 * k + 1], pf[16 * mt + 4 * k + 2], pf[16 * mt + 4 * k + 3], dI + k * 2);
        wg_commit();
        wg_wait<0>();
        fence_regs<0, 32>(az);
        if (!helper) {
          const int m = lane >> 3, r = lane & 7;
          const int sl = 2 * (m >> 1) + ((r >> 1) & 1) + 4 * (r >> 2);
          const uint32_t a0 = sb + OFF_XB + (2 * w + (m & 1)) * 2048 + sl * 64 + (((mt * 2 + (r & 1)) ^ (sl >> 1)) << 4);
#pragma unroll
          for (int i = 0; i < 4; i++)
            stsm4t(a0 + i * 512, pack_bf16(az[8 * i], az[8 * i + 1]), pack_bf16(az[8 * i + 2], az[8 * i + 3]), pack_bf16(az[8 * i + 4], az[8 * i + 5]),
                   pack_bf16(az[8 * i + 6], az[8 * i + 7]));
        }
      }
      if (helper) {
#pragma unroll
        for (int i = 0; i < 16; i++) {
          const int n = i >> 1, s0 = 8 * (n >> 1) + 2 * (n & 1) + (q & 1) + 4 * (q >> 1);
          if ((n & 1) == (int)(blockIdx.x & 1)) st_u2(g_Ts + s0 * 64 + 16 * w + g + 8 * (i & 1), pack_bf16(az[2 * i], az[2 * i + 1]), tag);
        }
        __syncwarp();
        if (lane == 0) hint_add(&g_cntH[0]);
        if (t == 0) { g_epoch[blockIdx.x * 8] = ep + 1; PROF_EV(13); }
      } else {
        asm volatile("fence.proxy.async.shared::cta;" ::: "memory");
        asm volatile("bar.sync 1, 128;" ::: "memory");
        if (t == 0) {
          PROF_EV(17);
          asm volatile("cp.async.bulk.tensor.3d.global.shared::cta.bulk_group [%0, {%2, %3, %4}], [%1];" ::"l"(&maps.ts), "r"(sb + OFF_XB),
                       "r"(32 * kg), "r"(0), "r"(8 * tn) : "memory");
          bulk_done_signal(&g_cntT[32 * j]);
          PROF_EV(13);
        }
        __syncwarp();
        if (j == 0) {
          hint_wait(&g_cntH[0], (ep + 1) * 8u);
          const uint32_t t0 = (uint32_t)clock();
          float2 v;
          do { v = ld_x2((const float2*)g_Ts + 2 * rb * 64 + t); spin_guard(t0); } while (__any_sync(0xffffffffu, (__float_as_uint(v.y) ^ tag) & 1));
          mbar_wait(bars + 8 * B_TL, 0);
          const uint32_t u = __float_as_uint(v.x);
          *(uint16_t*)(smem + OFF_T + t * 128 + ((t & 7) << 4)) = (uint16_t)u;
          *(uint16_t*)(smem + OFF_T + t * 128 + (((t & 7) ^ 1) << 4)) = (uint16_t)(u >> 16);
          asm volatile("fence.proxy.async.shared::cta;" ::: "memory");
          __syncwarp();
          if (lane == 0) mbar_arrive(bars + 8 * B_T);
        }
      }
    }
  } else {
    asm volatile("setmaxnreg.inc.sync.aligned.u32 192;");
    if (!helper) {
      const int wg = warp >> 2, w = warp & 3, g = lane >> 2, q = lane & 3;
      const bool elect = (tid & 127) == 0;
      const uint32_t ep = ld_x1(&g_epoch[blockIdx.x * 8]);
      float c1[64], cA[64], c2[64], ci[64], ct[64];
      const int zero = blockIdx.x >> 16;
      uint32_t h[56], yf[16];
      const uint32_t d0 = (sb & 0x3FFFF) >> 4;
      const uint32_t dK = d0 | (1u << 16), dN = d0 | (512u << 16), dM = d0 | (256u << 16);
      const uint32_t dX = dK + wg * 512;
      constexpr uint32_t RING = OFF_RING >> 4;
      auto waitA = [&](int n) { mbar_wait(bars + 8 * (B_FA + rslot(n)), rpar(n)); };
      auto freeA = [&](int n) { if (elect) mbar_arrive(bars + 8 * (B_EA + rslot(n))); };
      auto nop = [](int) {};

#pragma unroll
      for (int kb = 0; kb < 8; kb++) {
        if (kb == 0) asm volatile("bar.sync 0, 384;" ::: "memory");
        mbar_wait(bars + 8 * (B_FX + kb), 0); waitA(kb);
        wg_fence();
        const uint64_t dx = d128(dX + kb * 1024), df = d128(dK + RING + rslot(kb) * 1024), dm = d64(dM + RING + 512 + rslot(kb) * 1024);
        if (kb == 0) { mma_ss64<0, 0, 0>(c1, df, dx); mma_ss64<32, 1, 0>(c1, dx, dm); }
        else { mma_ss64<0, 0, 1>(c1, df, dx); mma_ss64<32, 1, 1>(c1, dx, dm); wg_commit(); wg_wait<1>(); freeA(kb - 1); }
#pragma unroll
        for (int k = 1; k < 4; k++) {
          mma_ss64<0, 0, 1>(c1, df + k * 2, dx + k * 2);
          mma_ss64<32, 1, 1>(c1, dx + k * 2, dm + k * 64);
        }
        wg_commit();
        if (kb == 0 && tid == 0) PROF_EV(1);
      }
      auto ffn_step = [&](auto first, float (&acc)[64], int n, int kb, auto done, auto work) {
        waitA(n);
        wg_fence();
        const uint64_t dx = d128(dX + kb * 1024), db = d128(dN + RING + rslot(n) * 1024);
        mma_ss128<0, 1, decltype(first)::value>(acc, dx, db, zero);
        wg_commit();
        wg_wait<1>();
        done();
#pragma unroll
        for (int k = 1; k < 4; k++) { mma_ss128<0, 1, 1>(acc, dx + k * 2, db + k * 128); work(k - 1); }
        wg_commit();
        work(3);
      };
      const uint32_t tag = (ep + 1) & 1;
      float hm[16];
      ffn_step(IC<0>(), c2, 8, 0, [&] { freeA(7); fence_regs<0, 64>(c1); }, [&](int i) {
#pragma unroll
        for (int e = 4 * i; e < 4 * i + 4; e++) { yf[e] = pack_pin(c1[2 * e], c1[2 * e + 1]); hm[e] = fmaxf(c1[32 + e], 0.f) * c1[48 + e]; }
      });
      fence_regs<0, 16>(hm);
      if (tid == 0) PROF_EV(2);
      {
        waitA(9); waitA(10);
        const uint64_t de = d128(dN + RING + (wg ? rslot(10) : rslot(9)) * 1024);
        wg_fence();
        mma_rs128<0, 1, 0>(cA, yf[0], yf[1], yf[2], yf[3], de);
        wg_commit();
        wg_wait<1>();
        freeA(8);
#pragma unroll
        for (int k = 1; k < 4; k++) mma_rs128<0, 1, 1>(cA, yf[4 * k], yf[4 * k + 1], yf[4 * k + 2], yf[4 * k + 3], de + k * 128);
        wg_commit();
      }
      {
        const int s0 = 2 * rb + wg, kr = 2 * ((s0 & 1) | ((s0 & 4) >> 1));
        const int m = lane >> 3, r = lane & 7;
        const uint32_t a0 = sb + OFF_XB + wg * 8192 + (((w >> 1) * 8 + (m >> 1)) * 2 + (w & 1)) * 256 + (m & 1) * 128 + ((r ^ (kr + (m & 1))) << 4);
        ffn_step(IC<1>(), c2, 11, 1, [&] { freeA(9); freeA(10); fence_regs<0, 64>(cA); }, [&](int i) {
          stsm4t(a0 + i * 1024, pack_bf16(cA[8 * i] - cA[34 + 8 * i], cA[8 * i + 1] - cA[35 + 8 * i]),
                 pack_bf16(cA[32 + 8 * i] + cA[8 * i + 2], cA[33 + 8 * i] + cA[8 * i + 3]),
                 pack_bf16(cA[8 * i + 4] - cA[38 + 8 * i], cA[8 * i + 5] - cA[39 + 8 * i]),
                 pack_bf16(cA[36 + 8 * i] + cA[8 * i + 6], cA[37 + 8 * i] + cA[8 * i + 7]));
        });
        if (j == 0 && w == 0 && g == 0) {
#pragma unroll
          for (int n = 0; n < 8; n++)
#pragma unroll
            for (int ce = 0; ce < 4; ce++)
              *(uint32_t*)(smem + OFF_SP + wg * 512 + ce * 128 + ((n ^ (kr + (ce & 1))) << 4) + 4 * q) =
                  pack_bf16(cA[(ce & 1) * 32 + 4 * n + (ce & 2)], cA[(ce & 1) * 32 + 4 * n + (ce & 2) + 1]);
        }
        asm volatile("fence.proxy.async.shared::cta;" ::: "memory");
        __syncwarp();
        if (lane == 0) mbar_arrive(bars + 8 * B_XS);
        if (tid == 0) PROF_EV(3);
      }
      const float* gp = g_gate + rb * 128 + wg * 64 + w * 16 + g;
      uint32_t gb0 = ld_x1(gp), gb1 = ld_x1(gp + 8);
#pragma unroll
      for (int kb = 2; kb < 7; kb++) ffn_step(IC<1>(), c2, 10 + kb, kb, [&] { freeA(9 + kb); }, nop);
      {
        const uint32_t t0 = (uint32_t)clock();
        while (__any_sync(0xffffffffu, ((gb0 ^ tag) | (gb1 ^ tag)) & 1)) { gb0 = ld_x1(gp); gb1 = ld_x1(gp + 8); spin_guard(t0); }
      }
      const float g0 = __uint_as_float(gb0 & ~1u), g1 = __uint_as_float(gb1 & ~1u);
      const float o0 = 1.0f - g0, o1 = 1.0f - g1;
      uint32_t hp[8];
      ffn_step(IC<1>(), c2, 17, 7, [&] { freeA(16); }, [&](int i) {
        hp[2 * i] = pack_pin(hm[4 * i] * o0, hm[4 * i + 1] * o0); hp[2 * i + 1] = pack_pin(hm[4 * i + 2] * o1, hm[4 * i + 3] * o1);
      });
      auto glu = [&](float (&acc)[64], int ho, int i0, int i1) {
#pragma unroll
        for (int i = i0; i < i1; i++) {
          const float o = (i & 1) ? o1 : o0;
          h[ho + i] = pack_pin(fmaxf(acc[2 * i], 0.f) * acc[32 + 2 * i] * o, fmaxf(acc[2 * i + 1], 0.f) * acc[33 + 2 * i] * o);
        }
      };
      ffn_step(IC<2>(), cA, 18, 0, [&] { freeA(17); fence_regs<0, 64>(c2); }, [&](int i) { glu(c2, 0, 2 * i, 2 * i + 2); });
      if (tid == 0) PROF_EV(4);
      ffn_step(IC<1>(), cA, 19, 1, [&] { freeA(18); }, [&](int i) { glu(c2, 0, 8 + 2 * i, 10 + 2 * i); });
#pragma unroll
      for (int kb = 2; kb < 8; kb++) ffn_step(IC<1>(), cA, 18 + kb, kb, [&] { freeA(17 + kb); }, nop);
      ffn_step(IC<2>(), c2, 26, 0, [&] { freeA(25); fence_regs<0, 64>(cA); }, [&](int i) { glu(cA, 16, 2 * i, 2 * i + 2); });
      if (tid == 0) PROF_EV(5);
      ffn_step(IC<1>(), c2, 27, 1, [&] { freeA(26); }, [&](int i) { glu(cA, 16, 8 + 2 * i, 10 + 2 * i); });
#pragma unroll
      for (int kb = 2; kb < 8; kb++)
        ffn_step(IC<1>(), c2, 26 + kb, kb, [&] {
          if (kb < 7) freeA(25 + kb);
          if (kb >= 3 && (kb & 1) && elect) mbar_arrive(bars + 8 * (B_ET + ((kb - 3) >> 1)));
        }, nop);
      wg_wait<0>();
      if (elect) mbar_arrive(bars + 8 * (B_ET + 3));
      fence_regs<0, 64>(c2);
      glu(c2, 32, 0, 16);
#pragma unroll
      for (int i = 0; i < 8; i++) h[48 + i] = hp[i] ^ zero;
      if (wg) waitA(35); else waitA(34);
      if (tid == 0) PROF_EV(6);
      mbar_wait(bars + 8 * (j == 0 ? B_T : B_TL), 0);
      if (tid == 0) PROF_EV(7);
      wg_fence();
      {
        const uint64_t dt = d128(dN + (OFF_T >> 4) + wg * 512), de = d128(dK + RING + (wg ? rslot(35) : rslot(34)) * 1024);
        mma_ss64<0, 1, 0>(ci, de, dt);
        mma_ss64<32, 1, 0>(ci, de + 512, dt);
#pragma unroll
        for (int k = 1; k < 4; k++) {
          mma_ss64<0, 1, 1>(ci, de + k * 2, dt + k * 128);
          mma_ss64<32, 1, 1>(ci, de + (512 + k * 2), dt + k * 128);
        }
      }
      wg_commit();

      auto head = [&](auto off, int t) {
        constexpr int O = decltype(off)::value;
        mbar_wait(bars + 8 * (B_FT + (t & 3)), t >> 2);
        const uint64_t db = d128(dN + (t & 3) * (TB >> 4));
        wg_fence();
        mma_rs64<O, 1, 0>(ct, h[0], h[1], h[2], h[3], db);
#pragma unroll
        for (int k = 1; k < 6; k++) mma_rs64<O, 1, 1>(ct, h[4 * k], h[4 * k + 1], h[4 * k + 2], h[4 * k + 3], db + k * 128);
        wg_commit();
        wg_wait<1>();
      };
      auto rest = [&](auto off, int t) {
        constexpr int O = decltype(off)::value;
        const uint64_t db = d128(dN + (t & 3) * (TB >> 4));
        wg_fence();
#pragma unroll
        for (int k = 6; k < 14; k++) mma_rs64<O, 1, 1>(ct, h[4 * k], h[4 * k + 1], h[4 * k + 2], h[4 * k + 3], db + k * 128);
#pragma unroll
        for (int k = 0; k < 4; k++) mma_rs64<O, 1, 1>(ct, yf[4 * k], yf[4 * k + 1], yf[4 * k + 2], yf[4 * k + 3], db + (14 + k) * 128);
        wg_commit();
      };
      auto freeT = [&](int t) { if (elect) mbar_arrive(bars + 8 * (B_ET + t)); };
      const uint32_t peerZ = mapa(sb + OFF_Z + tid * 16, rank ^ 1), peerB = mapa(bars + 8 * B_Z, rank ^ 1);
      auto send_peer = [&](auto off, int z) {
        constexpr int O = decltype(off)::value;
        fence_regs<O, 32>(ct);
#pragma unroll
        for (int i = 0; i < 4; i++)
          asm volatile("st.async.weak.shared::cluster.mbarrier::complete_tx::bytes.v4.b32 [%0], {%1,%2,%3,%4}, [%5];" ::"r"(peerZ + z * U + i * 4096),
                       "r"(pack_bf16(ct[O + 8 * i], ct[O + 8 * i + 1])), "r"(pack_bf16(ct[O + 8 * i + 2], ct[O + 8 * i + 3])),
                       "r"(pack_bf16(ct[O + 8 * i + 4], ct[O + 8 * i + 5])), "r"(pack_bf16(ct[O + 8 * i + 6], ct[O + 8 * i + 7])), "r"(peerB + 8 * z) : "memory");
      };
      auto send_grid = [&](auto off, int z) {
        constexpr int O = decltype(off)::value;
        fence_regs<O, 32>(ct);
        mbar_wait(bars + 8 * (B_Z + z), 0);
        uint4* dst = g_part + (size_t)((rb * 8 + 2 * ((q4 + z + 1) & 3) + rank) * 3 + z) * 1024 + tid;
#pragma unroll
        for (int i = 0; i < 4; i++) {
          const uint4 p = *(const uint4*)(smem + OFF_Z + z * U + i * 4096 + tid * 16);
          st_x4(dst + i * 256, (pack_bf16(ct[O + 8 * i] + bf_lo(p.x), ct[O + 8 * i + 1] + bf_hi(p.x)) & ~1u) | tag,
                pack_bf16(ct[O + 8 * i + 2] + bf_lo(p.y), ct[O + 8 * i + 3] + bf_hi(p.y)),
                pack_bf16(ct[O + 8 * i + 4] + bf_lo(p.z), ct[O + 8 * i + 5] + bf_hi(p.z)),
                pack_bf16(ct[O + 8 * i + 6] + bf_lo(p.w), ct[O + 8 * i + 7] + bf_hi(p.w)));
        }
        __syncwarp();
        if (lane == 0) hint_add(&g_cntP[32 * (rb * 8 + 2 * ((q4 + z + 1) & 3) + rank) + z]);
      };
      asm volatile("barrier.cluster.wait.aligned;" ::: "memory");
      head(IC<0>(), 0);
      if (elect) asm volatile("mbarrier.arrive.shared::cluster.b64 _, [%0];" ::"r"(mapa(bars + 8 * B_RDY, rank ^ 1)) : "memory");
      fence_regs<0, 64>(ci);
#pragma unroll
      for (int i = 0; i < 16; i++) {
        const float gg = ((i & 1) ? g1 : g0) * (2.0f / (2048.0f * 512.0f));
        if (i & 2) yf[i] = pack_pin((ci[2 * i] - ci[28 + 2 * i]) * gg, (ci[2 * i + 1] - ci[29 + 2 * i]) * gg);
        else yf[i] = pack_pin((ci[2 * i] + ci[36 + 2 * i]) * gg, (ci[2 * i + 1] + ci[37 + 2 * i]) * gg);
      }
      rest(IC<0>(), 0);
      if (tid == 0) PROF_EV(8);
      head(IC<32>(), 1); freeT(0); mbar_wait(bars + 8 * B_RDY, 0); send_peer(IC<0>(), 0); rest(IC<32>(), 1);
      head(IC<0>(), 2); freeT(1); send_peer(IC<32>(), 1); rest(IC<0>(), 2);
      head(IC<32>(), 3); freeT(2); send_peer(IC<0>(), 2); rest(IC<32>(), 3);
      head(IC<0>(), 4); freeT(3); send_grid(IC<32>(), 0); rest(IC<0>(), 4);
      head(IC<32>(), 5); send_grid(IC<0>(), 1); rest(IC<32>(), 5);
      head(IC<0>(), 6); send_grid(IC<32>(), 2); rest(IC<0>(), 6);
      head(IC<32>(), 7); send_peer(IC<0>(), 3);
      {
        const uint4* src = g_part + (size_t)(rb * 8 + j) * 3 * 1024 + tid;
        uint4 pv[12];
        mbar_wait(bars + 8 * (B_HP + 1), 0);
#pragma unroll
        for (int i = 0; i < 8; i++) pv[i] = ld_x4(src + i * 256);
        rest(IC<32>(), 7);
        if (tid == 0) PROF_EV(9);
        mbar_wait(bars + 8 * (B_HP + 2), 0);
        if (tid == 0) PROF_EV(24);
#pragma unroll
        for (int i = 8; i < 12; i++) pv[i] = ld_x4(src + i * 256);
        const uint32_t t0 = (uint32_t)clock();
        for (;;) {
          uint32_t bad = 0;
#pragma unroll
          for (int i = 0; i < 12; i++) bad |= pv[i].x ^ tag;
          if (!__any_sync(0xffffffffu, bad & 1)) break;
#pragma unroll
          for (int i = 0; i < 12; i++) pv[i] = ld_x4(src + i * 256);
          spin_guard(t0);
        }
        if (tid == 0) PROF_EV(14);
        float sum[32];
#pragma unroll
        for (int i = 0; i < 4; i++) {
          const uint32_t a[4] = {pv[i].x & ~1u, pv[i].y, pv[i].z, pv[i].w}, b[4] = {pv[4 + i].x & ~1u, pv[4 + i].y, pv[4 + i].z, pv[4 + i].w},
                         c[4] = {pv[8 + i].x & ~1u, pv[8 + i].y, pv[8 + i].z, pv[8 + i].w};
#pragma unroll
          for (int e = 0; e < 4; e++) {
            sum[8 * i + 2 * e] = bf_lo(a[e]) + bf_lo(b[e]) + bf_lo(c[e]);
            sum[8 * i + 2 * e + 1] = bf_hi(a[e]) + bf_hi(b[e]) + bf_hi(c[e]);
          }
        }
        mbar_wait(bars + 8 * (B_Z + 3), 0);
#pragma unroll
        for (int i = 0; i < 4; i++) {
          const uint4 p = *(const uint4*)(smem + OFF_Z + 3 * U + i * 4096 + tid * 16);
          const uint32_t a[4] = {p.x, p.y, p.z, p.w};
#pragma unroll
          for (int e = 0; e < 4; e++) { sum[8 * i + 2 * e] += bf_lo(a[e]); sum[8 * i + 2 * e + 1] += bf_hi(a[e]); }
        }
        wg_wait<0>();
        fence_regs<32, 32>(ct);
#pragma unroll
        for (int i = 0; i < 32; i++) sum[i] += ct[32 + i];
        const uint32_t stg = sb + OFF_T + warp * 2048;
        const int mr = (lane & 7) + ((lane >> 3) & 1) * 8, mc = lane >> 4;
#pragma unroll
        for (int i = 0; i < 4; i++) {
          const uint32_t a = stg + mr * 128 + (((2 * i + mc) ^ (mr & 7)) << 4);
          asm volatile("stmatrix.sync.aligned.m8n8.x4.shared.b16 [%0], {%1,%2,%3,%4};" ::"r"(a), "r"(pack_bf16(sum[8 * i], sum[8 * i + 1])),
                       "r"(pack_bf16(sum[8 * i + 2], sum[8 * i + 3])), "r"(pack_bf16(sum[8 * i + 4], sum[8 * i + 5])),
                       "r"(pack_bf16(sum[8 * i + 6], sum[8 * i + 7])) : "memory");
        }
        __syncwarp();
#pragma unroll
        for (int i = 0; i < 4; i++) {
          const int r = 4 * i + (lane >> 3), c = lane & 7;
          const uint4 v = *(const uint4*)(smem + OFF_T + warp * 2048 + r * 128 + ((c ^ (r & 7)) << 4));
          *(uint4*)(out + (size_t)(2 * rb + wg + 32 * (16 * w + r)) * 512 + 64 * j + 8 * c) = v;
        }
      }
      if (tid == 0) { g_epoch[blockIdx.x * 8] = ep + 1; PROF_EV(15); PROF_CK(41); }
    }
  }
}

typedef CUresult (*EncodeFn)(CUtensorMap*, CUtensorMapDataType, cuuint32_t, void*, const cuuint64_t*, const cuuint64_t*, const cuuint32_t*,
                             const cuuint32_t*, CUtensorMapInterleave, CUtensorMapSwizzle, CUtensorMapL2promotion, CUtensorMapFloatOOBfill);

static void encode(EncodeFn f, CUtensorMap* m, const void* base, int rank, const cuuint64_t* dims, const cuuint64_t* strides, const cuuint32_t* box,
                   CUtensorMapSwizzle sw) {
  cuuint32_t es[5] = {1, 1, 1, 1, 1};
  f(m, CU_TENSOR_MAP_DATA_TYPE_BFLOAT16, rank, (void*)base, dims, strides, box, es, CU_TENSOR_MAP_INTERLEAVE_NONE, sw,
    CU_TENSOR_MAP_L2_PROMOTION_L2_128B, CU_TENSOR_MAP_FLOAT_OOB_FILL_NONE);
}

extern "C" void kernel_launch(void* const* d_in, const int* in_sizes, int n_in, void* d_out, int out_size) {
  (void)in_sizes; (void)n_in; (void)out_size;
  const __nv_bfloat16* x = (const __nv_bfloat16*)d_in[0];
  const __nv_bfloat16* w_r = (const __nv_bfloat16*)d_in[1];
  const __nv_bfloat16* w_i = (const __nv_bfloat16*)d_in[2];
  const __nv_bfloat16* Wg = (const __nv_bfloat16*)d_in[4];
  const __nv_bfloat16* Wu = (const __nv_bfloat16*)d_in[5];
  const __nv_bfloat16* Wd = (const __nv_bfloat16*)d_in[6];
  const __nv_bfloat16* gw = (const __nv_bfloat16*)d_in[7];

  void* fp = nullptr; cudaDriverEntryPointQueryResult qr;
  cudaGetDriverEntryPoint("cuTensorMapEncodeTiled", &fp, cudaEnableDefault, &qr);
  EncodeFn enc = (EncodeFn)fp;
  void *pFT, *pET, *pX, *pT;
  cudaGetSymbolAddress(&pX, g_X); cudaGetSymbolAddress(&pT, g_T);
  cudaGetSymbolAddress(&pFT, g_FT); cudaGetSymbolAddress(&pET, g_ET);

  Maps mp;
  const CUtensorMapSwizzle S128 = CU_TENSOR_MAP_SWIZZLE_128B, S64 = CU_TENSOR_MAP_SWIZZLE_64B;
  { cuuint64_t d[3] = {512, 64, 32}, s[2] = {32768, 1024}; cuuint32_t b[3] = {64, 64, 2}; encode(enc, &mp.x, x, 3, d, s, b, S128); }
  { cuuint64_t d[2] = {512, 512}, s[1] = {1024}; cuuint32_t b[2] = {64, 64}; encode(enc, &mp.ft, pFT, 2, d, s, b, S128); }
  { cuuint64_t d[4] = {128, 32, 2, 129}, s[3] = {256, 8192, 16384}; cuuint32_t b[4] = {128, 1, 2, 16}; encode(enc, &mp.xs, pX, 4, d, s, b, CU_TENSOR_MAP_SWIZZLE_NONE); }
  { cuuint64_t d[3] = {512, 32, 64}, s[2] = {65536, 1024}; cuuint32_t b[3] = {32, 32, 8}; encode(enc, &mp.ts, pT, 3, d, s, b, S64); }
  { cuuint64_t d[3] = {512, 64, 32}, s[2] = {1024, 65536}; cuuint32_t b[3] = {64, 64, 2}; encode(enc, &mp.t, pT, 3, d, s, b, S128); }
  { cuuint64_t d[4] = {64, 64, 2, 32}, s[3] = {8192, 128, 256}; cuuint32_t b[4] = {64, 64, 2, 1}; encode(enc, &mp.e, pET, 4, d, s, b, S128); }
  { cuuint64_t d[2] = {1792, 512}, s[1] = {3584}; cuuint32_t b[2] = {64, 64}, b2[2] = {32, 64};
    encode(enc, &mp.g64, Wg, 2, d, s, b, S128); encode(enc, &mp.u64, Wu, 2, d, s, b, S128);
    encode(enc, &mp.g32, Wg, 2, d, s, b2, S64); encode(enc, &mp.u32, Wu, 2, d, s, b2, S64); }
  { cuuint64_t d[2] = {512, 1792}, s[1] = {1024}; cuuint32_t b[2] = {64, 192}, b2[2] = {64, 32};
    encode(enc, &mp.d192, Wd, 2, d, s, b, S128); encode(enc, &mp.d32, Wd, 2, d, s, b2, S128); }

  { cuuint64_t d[4] = {264, 32, 8, 8}, s[3] = {32896, 512, 4112}; cuuint32_t b[4] = {24, 32, 2, 1};
    encode(enc, &mp.wr, w_r, 4, d, s, b, CU_TENSOR_MAP_SWIZZLE_NONE); encode(enc, &mp.wi, w_i, 4, d, s, b, CU_TENSOR_MAP_SWIZZLE_NONE); }

  cudaFuncSetAttribute(fused_kernel, cudaFuncAttributeMaxDynamicSharedMemorySize, SMEM_BYTES);
  fused_kernel<<<NCTA, 512, SMEM_BYTES>>>(mp, x, w_r, w_i, gw, (__nv_bfloat16*)d_out);
}
```

```cpp
#include <cuda_runtime.h>
#include <cuda_bf16.h>
#include <cuda.h>
#include <stdint.h>

namespace tbl {
constexpr double PI = 3.14159265358979323846264338327950288;
constexpr double sin_s(double x) { double t = x, s = x; for (int n = 1; n < 12; n++) { t *= -x * x / ((2 * n) * (2 * n + 1)); s += t; } return s; }
constexpr double cos_s(double x) { double t = 1, s = 1; for (int n = 1; n < 12; n++) { t *= -x * x / ((2 * n - 1) * (2 * n)); s += t; } return s; }
constexpr double cos2048(int m) {
  m &= 2047; if (m > 1024) m = 2048 - m;
  bool neg = false; if (m > 512) { m = 1024 - m; neg = true; }
  double v = (m <= 256) ? cos_s(2 * PI * m / 2048) : sin_s(2 * PI * (512 - m) / 2048);
  return neg ? -v : v;
}
constexpr uint16_t to_bf16(double v) {
  if (v == 0) return 0;
  uint16_t s = 0; if (v < 0) { s = 0x8000; v = -v; }
  int e = 0; while (v >= 2) { v /= 2; e++; } while (v < 1) { v *= 2; e--; }
  double m = (v - 1) * 128; int mi = (int)m; double fr = m - mi;
  if (fr > 0.5 || (fr == 0.5 && (mi & 1))) mi++;
  if (mi == 128) { mi = 0; e++; }
  return (uint16_t)(s | ((e + 127) << 7) | mi);
}
struct CosT { uint16_t v[2048]; constexpr CosT() : v() { for (int i = 0; i < 2048; i++) v[i] = to_bf16(cos2048(i)); } };
struct alignas(1024) FT {
  uint16_t v[512 * 512];
  constexpr FT() : v() {
    CosT c;
    for (int r = 0; r < 512; r++) {
      int k = (r >> 4) * 8 + (r & 7), e = (r >> 3) & 1;
      int mul = 4 * k, add = e ? 512 : 0;
      if (k == 0 && e == 1) { mul = 1024; add = 0; }
      for (int d = 0; d < 512; d++) v[r * 512 + d] = c.v[(d * mul + add) & 2047];
    }
  }
};
struct alignas(1024) ET {
  uint16_t v[2048 * 128];
  constexpr ET() : v() {
    CosT c;
    for (int s = 0; s < 2048; s++)
      for (int j = 0; j < 64; j++) { v[s * 128 + j] = c.v[(s * j) & 2047]; v[s * 128 + 64 + j] = c.v[(s * j + 512) & 2047]; }
  }
};
struct alignas(1024) DT {
  uint16_t v[64 * 64];
  constexpr DT() : v() {
    CosT c;
    for (int r = 0; r < 64; r++)
      for (int n = 0; n < 64; n++) {
        const int sg = r >> 1, s0 = (sg & ~6) | ((sg & 2) << 1) | ((sg & 4) >> 1), e = r & 1, f = n & 1;
        const int m = 64 * s0 * (n >> 1) + (e == f ? 0 : e ? -512 : 512);
        v[r * 64 + (((n >> 3) ^ (r & 7)) << 3) + (n & 7)] = c.v[m & 2047];
      }
  }
};
}

__device__ constexpr tbl::FT g_FT = tbl::FT();
__device__ constexpr tbl::ET g_ET = tbl::ET();
__device__ constexpr tbl::DT g_DT = tbl::DT();

__device__ __align__(1024) uint16_t g_X[129 * 8192];
__device__ __align__(1024) uint16_t g_T[32 * 64 * 512];
__device__ __align__(1024) uint2 g_Ts[32 * 64];
__device__ __align__(1024) uint4 g_part[128 * 3 * 1024];
__device__ __align__(16) float g_gate[16 * 128];
__device__ __align__(16) uint2 g_Wh[2 * 2048];
__device__ unsigned g_epoch[132 * 8];
__device__ unsigned g_cntX[8 * 32], g_cntT[8 * 32], g_cntP[128 * 32], g_cntW[32], g_cntH[32];
#define PROF_EV(i) do {} while (0)
#define PROF_CK(i) do {} while (0)

__device__ __forceinline__ uint32_t smem_u32(const void* p) { return (uint32_t)__cvta_generic_to_shared(p); }
__device__ __forceinline__ void mbar_init(uint32_t bar, uint32_t cnt) { asm volatile("mbarrier.init.shared::cta.b64 [%0], %1;" ::"r"(bar), "r"(cnt)); }
__device__ __forceinline__ void mbar_expect_tx(uint32_t bar, uint32_t bytes) { asm volatile("mbarrier.arrive.expect_tx.shared::cta.b64 _, [%0], %1;" ::"r"(bar), "r"(bytes) : "memory"); }
__device__ __forceinline__ void mbar_arrive(uint32_t bar) { asm volatile("mbarrier.arrive.shared::cta.b64 _, [%0];" ::"r"(bar) : "memory"); }
__device__ __forceinline__ void mbar_wait(uint32_t bar, uint32_t parity) {
  asm volatile(
      "{\n.reg .pred p;\n.reg .u32 n;\nmov.u32 n, 0;\n"
      "W_LOOP:\nmbarrier.try_wait.parity.shared::cta.b64 p, [%0], %1;\n@p bra W_DONE;\n"
      "add.u32 n, n, 1;\nsetp.lt.u32 p, n, 0x40000;\n@p bra W_LOOP;\ntrap;\nW_DONE:\n}" ::"r"(bar), "r"(parity) : "memory");
}
__device__ __forceinline__ void bulk_load(uint32_t dst, const void* src, uint32_t bytes, uint32_t bar) {
  asm volatile("cp.async.bulk.shared::cluster.global.mbarrier::complete_tx::bytes [%0], [%1], %2, [%3];" ::"r"(dst), "l"(src), "r"(bytes), "r"(bar) : "memory");
}
__device__ __forceinline__ void cp16(uint32_t dst, const void* src) { asm volatile("cp.async.cg.shared.global [%0], [%1], 16;" ::"r"(dst), "l"(src) : "memory"); }
__device__ __forceinline__ void spin_guard(uint32_t t0) { if ((uint32_t)clock() - t0 > (1u << 30)) __trap(); }
__device__ __forceinline__ float tagf(float v, uint32_t tag) { return __uint_as_float((__float_as_uint(v) & ~1u) | tag); }
__device__ __forceinline__ float untag(float v) { return __uint_as_float(__float_as_uint(v) & ~1u); }
__device__ __forceinline__ void st_x2(float2* p, float a, float b) { asm volatile("st.relaxed.gpu.global.v2.f32 [%0], {%1,%2};" ::"l"(p), "f"(a), "f"(b) : "memory"); }
__device__ __forceinline__ float2 ld_x2(const float2* p) { float2 v; asm volatile("ld.relaxed.gpu.global.v2.f32 {%0,%1}, [%2];" : "=f"(v.x), "=f"(v.y) : "l"(p) : "memory"); return v; }
__device__ __forceinline__ void st_u2(uint2* p, uint32_t a, uint32_t b) { asm volatile("st.relaxed.gpu.global.v2.u32 [%0], {%1,%2};" ::"l"(p), "r"(a), "r"(b) : "memory"); }
__device__ __forceinline__ void prefetch2d(const CUtensorMap* m, int c0, int c1) { asm volatile("cp.async.bulk.prefetch.tensor.2d.L2.global [%0, {%1, %2}];" ::"l"(m), "r"(c0), "r"(c1) : "memory"); }
__device__ __forceinline__ void prefetch1d(const void* p, uint32_t bytes) { asm volatile("cp.async.bulk.prefetch.L2.global [%0], %1;" ::"l"(p), "r"(bytes) : "memory"); }
__device__ __forceinline__ uint32_t ld_x1(const void* p) { uint32_t v; asm volatile("ld.relaxed.gpu.global.u32 %0, [%1];" : "=r"(v) : "l"(p) : "memory"); return v; }
__device__ __forceinline__ uint4 ld_x4(const void* p) { uint4 v; asm volatile("ld.relaxed.gpu.global.v4.u32 {%0,%1,%2,%3}, [%4];" : "=r"(v.x), "=r"(v.y), "=r"(v.z), "=r"(v.w) : "l"(p) : "memory"); return v; }
__device__ __forceinline__ void st_x4(void* p, uint32_t a, uint32_t b, uint32_t c, uint32_t d) { asm volatile("st.relaxed.gpu.global.v4.u32 [%0], {%1,%2,%3,%4};" ::"l"(p), "r"(a), "r"(b), "r"(c), "r"(d) : "memory"); }
__device__ __forceinline__ uint32_t mapa(uint32_t a, uint32_t cta) { uint32_t r; asm volatile("mapa.shared::cluster.u32 %0, %1, %2;" : "=r"(r) : "r"(a), "r"(cta)); return r; }
__device__ __forceinline__ void stsm4t(uint32_t a, uint32_t r0, uint32_t r1, uint32_t r2, uint32_t r3) {
  asm volatile("stmatrix.sync.aligned.m8n8.x4.trans.shared.b16 [%0], {%1,%2,%3,%4};" ::"r"(a), "r"(r0), "r"(r1), "r"(r2), "r"(r3) : "memory");
}
__device__ __forceinline__ void hint_add(unsigned* p) { asm volatile("red.relaxed.gpu.global.add.u32 [%0], 1;" ::"l"(p) : "memory"); }
__device__ __forceinline__ void hint_wait(const unsigned* p, unsigned target) {
  const uint32_t t0 = (uint32_t)clock();
  while ((int)(ld_x1(p) - target) < 0) spin_guard(t0);
}
__device__ __forceinline__ void bulk_done_signal(unsigned* p) {
  asm volatile("cp.async.bulk.commit_group;\ncp.async.bulk.wait_group 0;\nfence.proxy.async.global;" ::: "memory");
  hint_add(p);
}
__device__ __forceinline__ void flag_wait(const unsigned* p, unsigned target) {
  hint_wait(p, target);
  asm volatile("fence.proxy.async.global;" ::: "memory");
}
__device__ __forceinline__ void tma2d(uint32_t dst, const CUtensorMap* m, uint32_t bar, int c0, int c1) {
  asm volatile("cp.async.bulk.tensor.2d.shared::cluster.global.mbarrier::complete_tx::bytes [%0], [%1, {%3, %4}], [%2];" ::"r"(dst), "l"(m), "r"(bar), "r"(c0), "r"(c1) : "memory");
}
__device__ __forceinline__ void tma3d(uint32_t dst, const CUtensorMap* m, uint32_t bar, int c0, int c1, int c2) {
  asm volatile("cp.async.bulk.tensor.3d.shared::cluster.global.mbarrier::complete_tx::bytes [%0], [%1, {%3, %4, %5}], [%2];" ::"r"(dst), "l"(m), "r"(bar), "r"(c0), "r"(c1), "r"(c2) : "memory");
}
__device__ __forceinline__ void tma4d(uint32_t dst, const CUtensorMap* m, uint32_t bar, int c0, int c1, int c2, int c3) {
  asm volatile("cp.async.bulk.tensor.4d.shared::cluster.global.mbarrier::complete_tx::bytes [%0], [%1, {%3, %4, %5, %6}], [%2];" ::"r"(dst), "l"(m), "r"(bar), "r"(c0), "r"(c1), "r"(c2), "r"(c3) : "memory");
}
__device__ __forceinline__ void wg_fence() { asm volatile("wgmma.fence.sync.aligned;" ::: "memory"); }
__device__ __forceinline__ void wg_commit() { asm volatile("wgmma.commit_group.sync.aligned;" ::: "memory"); }
template <int N> __device__ __forceinline__ void wg_wait() { asm volatile("wgmma.wait_group.sync.aligned %0;" ::"n"(N) : "memory"); }
template <int O, int N, int NN> __device__ __forceinline__ void fence_regs(float (&d)[NN]) {
#pragma unroll
  for (int i = 0; i < N; i++) asm volatile("" : "+f"(d[O + i])::"memory");
}
__device__ __forceinline__ uint32_t pack_bf16(float lo, float hi) {
  uint32_t r; asm("cvt.rn.bf16x2.f32 %0, %1, %2;" : "=r"(r) : "f"(hi), "f"(lo)); return r;
}
__device__ __forceinline__ uint32_t pack_pin(float lo, float hi) {
  uint32_t r; asm volatile("cvt.rn.bf16x2.f32 %0, %1, %2;" : "=r"(r) : "f"(hi), "f"(lo) : "memory"); return r;
}
__device__ __forceinline__ float bf_lo(uint32_t u) { return __uint_as_float(u << 16); }
__device__ __forceinline__ float bf_hi(uint32_t u) { return __uint_as_float(u & 0xffff0000u); }

__device__ __forceinline__ uint64_t d128(uint32_t lo) { uint64_t d; asm("mov.b64 %0, {%1, 0x40000040};" : "=l"(d) : "r"(lo)); return d; }
__device__ __forceinline__ uint64_t d64(uint32_t lo) { uint64_t d; asm("mov.b64 %0, {%1, 0x80000020};" : "=l"(d) : "r"(lo)); return d; }
template<int O,int TB,int ACC,int NN> __device__ __forceinline__ void mma_ss64(float (&d)[NN], uint64_t da, uint64_t db, int sd = 0){
  if constexpr (ACC == 1) asm volatile("wgmma.mma_async.sync.aligned.m64n64k16.f32.bf16.bf16 {%0,%1,%2,%3,%4,%5,%6,%7,%8,%9,%10,%11,%12,%13,%14,%15,%16,%17,%18,%19,%20,%21,%22,%23,%24,%25,%26,%27,%28,%29,%30,%31}, %32, %33, 1, 1, 1, %35, %34;"
   : "+f"(d[O+0]), "+f"(d[O+1]), "+f"(d[O+2]), "+f"(d[O+3]), "+f"(d[O+4]), "+f"(d[O+5]), "+f"(d[O+6]), "+f"(d[O+7]), "+f"(d[O+8]), "+f"(d[O+9]), "+f"(d[O+10]), "+f"(d[O+11]), "+f"(d[O+12]), "+f"(d[O+13]), "+f"(d[O+14]), "+f"(d[O+15]), "+f"(d[O+16]), "+f"(d[O+17]), "+f"(d[O+18]), "+f"(d[O+19]), "+f"(d[O+20]), "+f"(d[O+21]), "+f"(d[O+22]), "+f"(d[O+23]), "+f"(d[O+24]), "+f"(d[O+25]), "+f"(d[O+26]), "+f"(d[O+27]), "+f"(d[O+28]), "+f"(d[O+29]), "+f"(d[O+30]), "+f"(d[O+31])
   : "l"(da), "l"(db), "n"(TB & 1), "n"(TB >> 1));
  else if constexpr (ACC == 0) asm volatile("wgmma.mma_async.sync.aligned.m64n64k16.f32.bf16.bf16 {%0,%1,%2,%3,%4,%5,%6,%7,%8,%9,%10,%11,%12,%13,%14,%15,%16,%17,%18,%19,%20,%21,%22,%23,%24,%25,%26,%27,%28,%29,%30,%31}, %32, %33, 0, 1, 1, %35, %34;"
   : "=f"(d[O+0]), "=f"(d[O+1]), "=f"(d[O+2]), "=f"(d[O+3]), "=f"(d[O+4]), "=f"(d[O+5]), "=f"(d[O+6]), "=f"(d[O+7]), "=f"(d[O+8]), "=f"(d[O+9]), "=f"(d[O+10]), "=f"(d[O+11]), "=f"(d[O+12]), "=f"(d[O+13]), "=f"(d[O+14]), "=f"(d[O+15]), "=f"(d[O+16]), "=f"(d[O+17]), "=f"(d[O+18]), "=f"(d[O+19]), "=f"(d[O+20]), "=f"(d[O+21]), "=f"(d[O+22]), "=f"(d[O+23]), "=f"(d[O+24]), "=f"(d[O+25]), "=f"(d[O+26]), "=f"(d[O+27]), "=f"(d[O+28]), "=f"(d[O+29]), "=f"(d[O+30]), "=f"(d[O+31])
   : "l"(da), "l"(db), "n"(TB & 1), "n"(TB >> 1));
  else asm volatile("{\n.reg .pred p;\nsetp.ne.b32 p, %36, 0;\nwgmma.mma_async.sync.aligned.m64n64k16.f32.bf16.bf16 {%0,%1,%2,%3,%4,%5,%6,%7,%8,%9,%10,%11,%12,%13,%14,%15,%16,%17,%18,%19,%20,%21,%22,%23,%24,%25,%26,%27,%28,%29,%30,%31}, %32, %33, p, 1, 1, %35, %34;\n}"
   : "+f"(d[O+0]), "+f"(d[O+1]), "+f"(d[O+2]), "+f"(d[O+3]), "+f"(d[O+4]), "+f"(d[O+5]), "+f"(d[O+6]), "+f"(d[O+7]), "+f"(d[O+8]), "+f"(d[O+9]), "+f"(d[O+10]), "+f"(d[O+11]), "+f"(d[O+12]), "+f"(d[O+13]), "+f"(d[O+14]), "+f"(d[O+15]), "+f"(d[O+16]), "+f"(d[O+17]), "+f"(d[O+18]), "+f"(d[O+19]), "+f"(d[O+20]), "+f"(d[O+21]), "+f"(d[O+22]), "+f"(d[O+23]), "+f"(d[O+24]), "+f"(d[O+25]), "+f"(d[O+26]), "+f"(d[O+27]), "+f"(d[O+28]), "+f"(d[O+29]), "+f"(d[O+30]), "+f"(d[O+31])
   : "l"(da), "l"(db), "n"(TB & 1), "n"(TB >> 1), "r"(sd));
}
template<int O,int TB,int ACC,int NN> __device__ __forceinline__ void mma_rs64(float (&d)[NN], uint32_t a0, uint32_t a1, uint32_t a2, uint32_t a3, uint64_t db, int sd = 0){
  if constexpr (ACC == 1) asm volatile("wgmma.mma_async.sync.aligned.m64n64k16.f32.bf16.bf16 {%0,%1,%2,%3,%4,%5,%6,%7,%8,%9,%10,%11,%12,%13,%14,%15,%16,%17,%18,%19,%20,%21,%22,%23,%24,%25,%26,%27,%28,%29,%30,%31}, {%32,%33,%34,%35}, %36, 1, 1, 1, %37;"
   : "+f"(d[O+0]), "+f"(d[O+1]), "+f"(d[O+2]), "+f"(d[O+3]), "+f"(d[O+4]), "+f"(d[O+5]), "+f"(d[O+6]), "+f"(d[O+7]), "+f"(d[O+8]), "+f"(d[O+9]), "+f"(d[O+10]), "+f"(d[O+11]), "+f"(d[O+12]), "+f"(d[O+13]), "+f"(d[O+14]), "+f"(d[O+15]), "+f"(d[O+16]), "+f"(d[O+17]), "+f"(d[O+18]), "+f"(d[O+19]), "+f"(d[O+20]), "+f"(d[O+21]), "+f"(d[O+22]), "+f"(d[O+23]), "+f"(d[O+24]), "+f"(d[O+25]), "+f"(d[O+26]), "+f"(d[O+27]), "+f"(d[O+28]), "+f"(d[O+29]), "+f"(d[O+30]), "+f"(d[O+31])
   : "r"(a0), "r"(a1), "r"(a2), "r"(a3), "l"(db), "n"(TB));
  else if constexpr (ACC == 0) asm volatile("wgmma.mma_async.sync.aligned.m64n64k16.f32.bf16.bf16 {%0,%1,%2,%3,%4,%5,%6,%7,%8,%9,%10,%11,%12,%13,%14,%15,%16,%17,%18,%19,%20,%21,%22,%23,%24,%25,%26,%27,%28,%29,%30,%31}, {%32,%33,%34,%35}, %36, 0, 1, 1, %37;"
   : "=f"(d[O+0]), "=f"(d[O+1]), "=f"(d[O+2]), "=f"(d[O+3]), "=f"(d[O+4]), "=f"(d[O+5]), "=f"(d[O+6]), "=f"(d[O+7]), "=f"(d[O+8]), "=f"(d[O+9]), "=f"(d[O+10]), "=f"(d[O+11]), "=f"(d[O+12]), "=f"(d[O+13]), "=f"(d[O+14]), "=f"(d[O+15]), "=f"(d[O+16]), "=f"(d[O+17]), "=f"(d[O+18]), "=f"(d[O+19]), "=f"(d[O+20]), "=f"(d[O+21]), "=f"(d[O+22]), "=f"(d[O+23]), "=f"(d[O+24]), "=f"(d[O+25]), "=f"(d[O+26]), "=f"(d[O+27]), "=f"(d[O+28]), "=f"(d[O+29]), "=f"(d[O+30]), "=f"(d[O+31])
   : "r"(a0), "r"(a1), "r"(a2), "r"(a3), "l"(db), "n"(TB));
  else asm volatile("{\n.reg .pred p;\nsetp.ne.b32 p, %38, 0;\nwgmma.mma_async.sync.aligned.m64n64k16.f32.bf16.bf16 {%0,%1,%2,%3,%4,%5,%6,%7,%8,%9,%10,%11,%12,%13,%14,%15,%16,%17,%18,%19,%20,%21,%22,%23,%24,%25,%26,%27,%28,%29,%30,%31}, {%32,%33,%34,%35}, %36, p, 1, 1, %37;\n}"
   : "+f"(d[O+0]), "+f"(d[O+1]), "+f"(d[O+2]), "+f"(d[O+3]), "+f"(d[O+4]), "+f"(d[O+5]), "+f"(d[O+6]), "+f"(d[O+7]), "+f"(d[O+8]), "+f"(d[O+9]), "+f"(d[O+10]), "+f"(d[O+11]), "+f"(d[O+12]), "+f"(d[O+13]), "+f"(d[O+14]), "+f"(d[O+15]), "+f"(d[O+16]), "+f"(d[O+17]), "+f"(d[O+18]), "+f"(d[O+19]), "+f"(d[O+20]), "+f"(d[O+21]), "+f"(d[O+22]), "+f"(d[O+23]), "+f"(d[O+24]), "+f"(d[O+25]), "+f"(d[O+26]), "+f"(d[O+27]), "+f"(d[O+28]), "+f"(d[O+29]), "+f"(d[O+30]), "+f"(d[O+31])
   : "r"(a0), "r"(a1), "r"(a2), "r"(a3), "l"(db), "n"(TB), "r"(sd));
}
template<int O,int TB,int ACC,int NN> __device__ __forceinline__ void mma_ss128(float (&d)[NN], uint64_t da, uint64_t db, int sd = 0){
  if constexpr (ACC == 1) asm volatile("wgmma.mma_async.sync.aligned.m64n128k16.f32.bf16.bf16 {%0,%1,%2,%3,%4,%5,%6,%7,%8,%9,%10,%11,%12,%13,%14,%15,%16,%17,%18,%19,%20,%21,%22,%23,%24,%25,%26,%27,%28,%29,%30,%31,%32,%33,%34,%35,%36,%37,%38,%39,%40,%41,%42,%43,%44,%45,%46,%47,%48,%49,%50,%51,%52,%53,%54,%55,%56,%57,%58,%59,%60,%61,%62,%63}, %64, %65, 1, 1, 1, %67, %66;"
   : "+f"(d[O+0]), "+f"(d[O+1]), "+f"(d[O+2]), "+f"(d[O+3]), "+f"(d[O+4]), "+f"(d[O+5]), "+f"(d[O+6]), "+f"(d[O+7]), "+f"(d[O+8]), "+f"(d[O+9]), "+f"(d[O+10]), "+f"(d[O+11]), "+f"(d[O+12]), "+f"(d[O+13]), "+f"(d[O+14]), "+f"(d[O+15]), "+f"(d[O+16]), "+f"(d[O+17]), "+f"(d[O+18]), "+f"(d[O+19]), "+f"(d[O+20]), "+f"(d[O+21]), "+f"(d[O+22]), "+f"(d[O+23]), "+f"(d[O+24]), "+f"(d[O+25]), "+f"(d[O+26]), "+f"(d[O+27]), "+f"(d[O+28]), "+f"(d[O+29]), "+f"(d[O+30]), "+f"(d[O+31]), "+f"(d[O+32]), "+f"(d[O+33]), "+f"(d[O+34]), "+f"(d[O+35]), "+f"(d[O+36]), "+f"(d[O+37]), "+f"(d[O+38]), "+f"(d[O+39]), "+f"(d[O+40]), "+f"(d[O+41]), "+f"(d[O+42]), "+f"(d[O+43]), "+f"(d[O+44]), "+f"(d[O+45]), "+f"(d[O+46]), "+f"(d[O+47]), "+f"(d[O+48]), "+f"(d[O+49]), "+f"(d[O+50]), "+f"(d[O+51]), "+f"(d[O+52]), "+f"(d[O+53]), "+f"(d[O+54]), "+f"(d[O+55]), "+f"(d[O+56]), "+f"(d[O+57]), "+f"(d[O+58]), "+f"(d[O+59]), "+f"(d[O+60]), "+f"(d[O+61]), "+f"(d[O+62]), "+f"(d[O+63])
   : "l"(da), "l"(db), "n"(TB & 1), "n"(TB >> 1));
  else if constexpr (ACC == 0) asm volatile("wgmma.mma_async.sync.aligned.m64n128k16.f32.bf16.bf16 {%0,%1,%2,%3,%4,%5,%6,%7,%8,%9,%10,%11,%12,%13,%14,%15,%16,%17,%18,%19,%20,%21,%22,%23,%24,%25,%26,%27,%28,%29,%30,%31,%32,%33,%34,%35,%36,%37,%38,%39,%40,%41,%42,%43,%44,%45,%46,%47,%48,%49,%50,%51,%52,%53,%54,%55,%56,%57,%58,%59,%60,%61,%62,%63}, %64, %65, 0, 1, 1, %67, %66;"
   : "=f"(d[O+0]), "=f"(d[O+1]), "=f"(d[O+2]), "=f"(d[O+3]), "=f"(d[O+4]), "=f"(d[O+5]), "=f"(d[O+6]), "=f"(d[O+7]), "=f"(d[O+8]), "=f"(d[O+9]), "=f"(d[O+10]), "=f"(d[O+11]), "=f"(d[O+12]), "=f"(d[O+13]), "=f"(d[O+14]), "=f"(d[O+15]), "=f"(d[O+16]), "=f"(d[O+17]), "=f"(d[O+18]), "=f"(d[O+19]), "=f"(d[O+20]), "=f"(d[O+21]), "=f"(d[O+22]), "=f"(d[O+23]), "=f"(d[O+24]), "=f"(d[O+25]), "=f"(d[O+26]), "=f"(d[O+27]), "=f"(d[O+28]), "=f"(d[O+29]), "=f"(d[O+30]), "=f"(d[O+31]), "=f"(d[O+32]), "=f"(d[O+33]), "=f"(d[O+34]), "=f"(d[O+35]), "=f"(d[O+36]), "=f"(d[O+37]), "=f"(d[O+38]), "=f"(d[O+39]), "=f"(d[O+40]), "=f"(d[O+41]), "=f"(d[O+42]), "=f"(d[O+43]), "=f"(d[O+44]), "=f"(d[O+45]), "=f"(d[O+46]), "=f"(d[O+47]), "=f"(d[O+48]), "=f"(d[O+49]), "=f"(d[O+50]), "=f"(d[O+51]), "=f"(d[O+52]), "=f"(d[O+53]), "=f"(d[O+54]), "=f"(d[O+55]), "=f"(d[O+56]), "=f"(d[O+57]), "=f"(d[O+58]), "=f"(d[O+59]), "=f"(d[O+60]), "=f"(d[O+61]), "=f"(d[O+62]), "=f"(d[O+63])
   : "l"(da), "l"(db), "n"(TB & 1), "n"(TB >> 1));
  else asm volatile("{\n.reg .pred p;\nsetp.ne.b32 p, %68, 0;\nwgmma.mma_async.sync.aligned.m64n128k16.f32.bf16.bf16 {%0,%1,%2,%3,%4,%5,%6,%7,%8,%9,%10,%11,%12,%13,%14,%15,%16,%17,%18,%19,%20,%21,%22,%23,%24,%25,%26,%27,%28,%29,%30,%31,%32,%33,%34,%35,%36,%37,%38,%39,%40,%41,%42,%43,%44,%45,%46,%47,%48,%49,%50,%51,%52,%53,%54,%55,%56,%57,%58,%59,%60,%61,%62,%63}, %64, %65, p, 1, 1, %67, %66;\n}"
   : "+f"(d[O+0]), "+f"(d[O+1]), "+f"(d[O+2]), "+f"(d[O+3]), "+f"(d[O+4]), "+f"(d[O+5]), "+f"(d[O+6]), "+f"(d[O+7]), "+f"(d[O+8]), "+f"(d[O+9]), "+f"(d[O+10]), "+f"(d[O+11]), "+f"(d[O+12]), "+f"(d[O+13]), "+f"(d[O+14]), "+f"(d[O+15]), "+f"(d[O+16]), "+f"(d[O+17]), "+f"(d[O+18]), "+f"(d[O+19]), "+f"(d[O+20]), "+f"(d[O+21]), "+f"(d[O+22]), "+f"(d[O+23]), "+f"(d[O+24]), "+f"(d[O+25]), "+f"(d[O+26]), "+f"(d[O+27]), "+f"(d[O+28]), "+f"(d[O+29]), "+f"(d[O+30]), "+f"(d[O+31]), "+f"(d[O+32]), "+f"(d[O+33]), "+f"(d[O+34]), "+f"(d[O+35]), "+f"(d[O+36]), "+f"(d[O+37]), "+f"(d[O+38]), "+f"(d[O+39]), "+f"(d[O+40]), "+f"(d[O+41]), "+f"(d[O+42]), "+f"(d[O+43]), "+f"(d[O+44]), "+f"(d[O+45]), "+f"(d[O+46]), "+f"(d[O+47]), "+f"(d[O+48]), "+f"(d[O+49]), "+f"(d[O+50]), "+f"(d[O+51]), "+f"(d[O+52]), "+f"(d[O+53]), "+f"(d[O+54]), "+f"(d[O+55]), "+f"(d[O+56]), "+f"(d[O+57]), "+f"(d[O+58]), "+f"(d[O+59]), "+f"(d[O+60]), "+f"(d[O+61]), "+f"(d[O+62]), "+f"(d[O+63])
   : "l"(da), "l"(db), "n"(TB & 1), "n"(TB >> 1), "r"(sd));
}
template<int O,int TB,int ACC,int NN> __device__ __forceinline__ void mma_rs128(float (&d)[NN], uint32_t a0, uint32_t a1, uint32_t a2, uint32_t a3, uint64_t db, int sd = 0){
  if constexpr (ACC == 1) asm volatile("wgmma.mma_async.sync.aligned.m64n128k16.f32.bf16.bf16 {%0,%1,%2,%3,%4,%5,%6,%7,%8,%9,%10,%11,%12,%13,%14,%15,%16,%17,%18,%19,%20,%21,%22,%23,%24,%25,%26,%27,%28,%29,%30,%31,%32,%33,%34,%35,%36,%37,%38,%39,%40,%41,%42,%43,%44,%45,%46,%47,%48,%49,%50,%51,%52,%53,%54,%55,%56,%57,%58,%59,%60,%61,%62,%63}, {%64,%65,%66,%67}, %68, 1, 1, 1, %69;"
   : "+f"(d[O+0]), "+f"(d[O+1]), "+f"(d[O+2]), "+f"(d[O+3]), "+f"(d[O+4]), "+f"(d[O+5]), "+f"(d[O+6]), "+f"(d[O+7]), "+f"(d[O+8]), "+f"(d[O+9]), "+f"(d[O+10]), "+f"(d[O+11]), "+f"(d[O+12]), "+f"(d[O+13]), "+f"(d[O+14]), "+f"(d[O+15]), "+f"(d[O+16]), "+f"(d[O+17]), "+f"(d[O+18]), "+f"(d[O+19]), "+f"(d[O+20]), "+f"(d[O+21]), "+f"(d[O+22]), "+f"(d[O+23]), "+f"(d[O+24]), "+f"(d[O+25]), "+f"(d[O+26]), "+f"(d[O+27]), "+f"(d[O+28]), "+f"(d[O+29]), "+f"(d[O+30]), "+f"(d[O+31]), "+f"(d[O+32]), "+f"(d[O+33]), "+f"(d[O+34]), "+f"(d[O+35]), "+f"(d[O+36]), "+f"(d[O+37]), "+f"(d[O+38]), "+f"(d[O+39]), "+f"(d[O+40]), "+f"(d[O+41]), "+f"(d[O+42]), "+f"(d[O+43]), "+f"(d[O+44]), "+f"(d[O+45]), "+f"(d[O+46]), "+f"(d[O+47]), "+f"(d[O+48]), "+f"(d[O+49]), "+f"(d[O+50]), "+f"(d[O+51]), "+f"(d[O+52]), "+f"(d[O+53]), "+f"(d[O+54]), "+f"(d[O+55]), "+f"(d[O+56]), "+f"(d[O+57]), "+f"(d[O+58]), "+f"(d[O+59]), "+f"(d[O+60]), "+f"(d[O+61]), "+f"(d[O+62]), "+f"(d[O+63])
   : "r"(a0), "r"(a1), "r"(a2), "r"(a3), "l"(db), "n"(TB));
  else if constexpr (ACC == 0) asm volatile("wgmma.mma_async.sync.aligned.m64n128k16.f32.bf16.bf16 {%0,%1,%2,%3,%4,%5,%6,%7,%8,%9,%10,%11,%12,%13,%14,%15,%16,%17,%18,%19,%20,%21,%22,%23,%24,%25,%26,%27,%28,%29,%30,%31,%32,%33,%34,%35,%36,%37,%38,%39,%40,%41,%42,%43,%44,%45,%46,%47,%48,%49,%50,%51,%52,%53,%54,%55,%56,%57,%58,%59,%60,%61,%62,%63}, {%64,%65,%66,%67}, %68, 0, 1, 1, %69;"
   : "=f"(d[O+0]), "=f"(d[O+1]), "=f"(d[O+2]), "=f"(d[O+3]), "=f"(d[O+4]), "=f"(d[O+5]), "=f"(d[O+6]), "=f"(d[O+7]), "=f"(d[O+8]), "=f"(d[O+9]), "=f"(d[O+10]), "=f"(d[O+11]), "=f"(d[O+12]), "=f"(d[O+13]), "=f"(d[O+14]), "=f"(d[O+15]), "=f"(d[O+16]), "=f"(d[O+17]), "=f"(d[O+18]), "=f"(d[O+19]), "=f"(d[O+20]), "=f"(d[O+21]), "=f"(d[O+22]), "=f"(d[O+23]), "=f"(d[O+24]), "=f"(d[O+25]), "=f"(d[O+26]), "=f"(d[O+27]), "=f"(d[O+28]), "=f"(d[O+29]), "=f"(d[O+30]), "=f"(d[O+31]), "=f"(d[O+32]), "=f"(d[O+33]), "=f"(d[O+34]), "=f"(d[O+35]), "=f"(d[O+36]), "=f"(d[O+37]), "=f"(d[O+38]), "=f"(d[O+39]), "=f"(d[O+40]), "=f"(d[O+41]), "=f"(d[O+42]), "=f"(d[O+43]), "=f"(d[O+44]), "=f"(d[O+45]), "=f"(d[O+46]), "=f"(d[O+47]), "=f"(d[O+48]), "=f"(d[O+49]), "=f"(d[O+50]), "=f"(d[O+51]), "=f"(d[O+52]), "=f"(d[O+53]), "=f"(d[O+54]), "=f"(d[O+55]), "=f"(d[O+56]), "=f"(d[O+57]), "=f"(d[O+58]), "=f"(d[O+59]), "=f"(d[O+60]), "=f"(d[O+61]), "=f"(d[O+62]), "=f"(d[O+63])
   : "r"(a0), "r"(a1), "r"(a2), "r"(a3), "l"(db), "n"(TB));
  else asm volatile("{\n.reg .pred p;\nsetp.ne.b32 p, %70, 0;\nwgmma.mma_async.sync.aligned.m64n128k16.f32.bf16.bf16 {%0,%1,%2,%3,%4,%5,%6,%7,%8,%9,%10,%11,%12,%13,%14,%15,%16,%17,%18,%19,%20,%21,%22,%23,%24,%25,%26,%27,%28,%29,%30,%31,%32,%33,%34,%35,%36,%37,%38,%39,%40,%41,%42,%43,%44,%45,%46,%47,%48,%49,%50,%51,%52,%53,%54,%55,%56,%57,%58,%59,%60,%61,%62,%63}, {%64,%65,%66,%67}, %68, p, 1, 1, %69;\n}"
   : "+f"(d[O+0]), "+f"(d[O+1]), "+f"(d[O+2]), "+f"(d[O+3]), "+f"(d[O+4]), "+f"(d[O+5]), "+f"(d[O+6]), "+f"(d[O+7]), "+f"(d[O+8]), "+f"(d[O+9]), "+f"(d[O+10]), "+f"(d[O+11]), "+f"(d[O+12]), "+f"(d[O+13]), "+f"(d[O+14]), "+f"(d[O+15]), "+f"(d[O+16]), "+f"(d[O+17]), "+f"(d[O+18]), "+f"(d[O+19]), "+f"(d[O+20]), "+f"(d[O+21]), "+f"(d[O+22]), "+f"(d[O+23]), "+f"(d[O+24]), "+f"(d[O+25]), "+f"(d[O+26]), "+f"(d[O+27]), "+f"(d[O+28]), "+f"(d[O+29]), "+f"(d[O+30]), "+f"(d[O+31]), "+f"(d[O+32]), "+f"(d[O+33]), "+f"(d[O+34]), "+f"(d[O+35]), "+f"(d[O+36]), "+f"(d[O+37]), "+f"(d[O+38]), "+f"(d[O+39]), "+f"(d[O+40]), "+f"(d[O+41]), "+f"(d[O+42]), "+f"(d[O+43]), "+f"(d[O+44]), "+f"(d[O+45]), "+f"(d[O+46]), "+f"(d[O+47]), "+f"(d[O+48]), "+f"(d[O+49]), "+f"(d[O+50]), "+f"(d[O+51]), "+f"(d[O+52]), "+f"(d[O+53]), "+f"(d[O+54]), "+f"(d[O+55]), "+f"(d[O+56]), "+f"(d[O+57]), "+f"(d[O+58]), "+f"(d[O+59]), "+f"(d[O+60]), "+f"(d[O+61]), "+f"(d[O+62]), "+f"(d[O+63])
   : "r"(a0), "r"(a1), "r"(a2), "r"(a3), "l"(db), "n"(TB), "r"(sd));
}

#define NEARLY 0
#define XAHEAD 3
#define WAFTER 7
#define WPACE 100
#define GATE_AT 0
#define TPACE 40
#define PFMODE 0
#define MAPMODE 0
template <int V> struct IC { static constexpr int value = V; };
struct Maps { CUtensorMap x, ft, g32, u32, wr, wi, g64, u64, e, xs, ts, t, d192, d32; };

constexpr int NCTA = 130;
constexpr int U = 16384;
constexpr int TB = 36864;
constexpr int NR = 4;
constexpr int OFF_RING = 8 * U, OFF_Z = 9 * U, OFF_XB = 12 * U, OFF_T = 13 * U, OFF_D = OFF_T, OFF_SP = OFF_T + 12288;
constexpr int OFF_BAR = 14 * U;
constexpr int SMEM_BYTES = OFF_BAR + 512;
constexpr int B_FX = 0, B_FA = 8, B_FT = 12, B_Z = 16, B_W = 20, B_HX = 21, B_TL = 22, B_HP = 23, B_WR = 26;
constexpr int B_EA = 30, B_ET = 34, B_RDY = 38;
constexpr int B_T = 39, B_XS = 40, NBAR = 41;
__host__ __device__ constexpr int rslot(int n) { return n % NR; }
__host__ __device__ constexpr int rpar(int n) { return (n / NR) & 1; }

__global__ void __cluster_dims__(2, 1, 1) __launch_bounds__(512, 1)
fused_kernel(const __grid_constant__ Maps maps, const __nv_bfloat16* __restrict__ x, const __nv_bfloat16* __restrict__ w_r,
             const __nv_bfloat16* __restrict__ w_i, const __nv_bfloat16* __restrict__ gate_w, __nv_bfloat16* __restrict__ out) {
  extern __shared__ __align__(1024) uint8_t smem[];
  const uint32_t sb = smem_u32(smem);
  const uint32_t bars = sb + OFF_BAR;
  const int tid = threadIdx.x, lane = tid & 31;
  const int warp = __shfl_sync(0xffffffffu, tid >> 5, 0);
  const bool helper = blockIdx.x >= 128;
  const int cl = (blockIdx.x >> 1) & 63, rank = blockIdx.x & 1;
  const int q4 = cl & 3, rb = cl >> 2;
  const int j = 2 * q4 + rank;
  const int f_full = 448 * q4 + (rank ? 256 : 0);
  const int f_half = 448 * q4 + (rank ? 224 : 192);
  const int kg = 2 * j + (rb >> 3), tn = rb & 7;

  if (tid == 64) { PROF_EV(0); PROF_CK(40); }
  auto ring_part = [&](int p, int n, int slot) {
    const uint32_t fb = bars + 8 * (B_FA + slot), dst = sb + OFF_RING + slot * U;
    const bool table = n == 9 || n == 10 || n >= 34;
    const int q = n == 8 ? 0 : n - 10;
    if (p == 0) {
      mbar_expect_tx(fb, U);
      if (n < 8) tma2d(dst, &maps.ft, fb, 64 * n, 64 * j);
      else if (table) tma4d(dst, &maps.e, fb, 0, 0, 0, 2 * rb + (n >= 34 ? n - 34 : n - 9));
      else tma2d(dst, &maps.g64, fb, f_full + 64 * (q >> 3), 64 * (q & 7));
    } else if (p == 1) {
      if (n < 8) { tma2d(dst + 8192, &maps.g32, fb, f_half, 64 * n); tma2d(dst + 12288, &maps.u32, fb, f_half, 64 * n); }
      else if (!table) tma2d(dst + 8192, &maps.u64, fb, f_full + 64 * (q >> 3), 64 * (q & 7));
    }
  };
  auto x_load = [&](int q) {
    mbar_expect_tx(bars + 8 * (B_FX + q), U);
    tma3d(sb + q * U, &maps.x, bars + 8 * (B_FX + q), 64 * q, 0, 2 * rb);
  };
  if (warp >= 12) {
    if (warp < 14) {
      if (lane == 0) {
#pragma unroll
        for (int i = 0; i < 6; i++) mbar_init(bars + 8 * (2 * i + warp - 12), 1);
        asm volatile("fence.proxy.async.shared::cta;" ::: "memory");
      }
      __syncwarp();
      asm volatile("bar.arrive 0, 384;" ::: "memory");
      asm volatile("bar.arrive 4, 256;" ::: "memory");
      if (lane == 0) {
        if (!helper) {
#pragma unroll 1
          for (int n = warp - 12; n < NR; n += 2) {
            const uint32_t fb = bars + 8 * (B_FA + n), dst = sb + OFF_RING + n * U;
            x_load(n);
            mbar_expect_tx(fb, U);
            tma2d(dst, &maps.ft, fb, 64 * n, 64 * j);
            tma2d(dst + 8192, &maps.g32, fb, f_half, 64 * n);
            tma2d(dst + 12288, &maps.u32, fb, f_half, 64 * n);
          }
        }
      }
    } else {
      if (lane != 0) {
      } else if (warp == 15) {
#pragma unroll
        for (int i = B_FT; i < NBAR; i++) mbar_init(bars + 8 * i, i < B_EA ? 1 : i < B_T ? 2 : i < B_XS ? 4 : 8);
#pragma unroll
        for (int i = 0; i < 4; i++) mbar_expect_tx(bars + 8 * (B_Z + i), U);
        asm volatile("fence.mbarrier_init.release.cluster;" ::: "memory");
        asm volatile("fence.proxy.async.shared::cta;" ::: "memory");
      } else {
#pragma unroll
        for (int i = 1; i < 4; i++) asm volatile("prefetch.tensormap [%0];" ::"l"((const char*)&maps + i * 128) : "memory");
      }
      __syncwarp();
      asm volatile("bar.arrive 0, 384;" ::: "memory");
      asm volatile("bar.arrive 4, 256;" ::: "memory");
    }
    __syncwarp();
  }
  asm volatile("barrier.cluster.arrive.relaxed.aligned;" ::: "memory");
  if (tid == 64) PROF_EV(38);

  if (warp >= 12) {
    asm volatile("setmaxnreg.dec.sync.aligned.u32 24;");
    asm volatile("bar.sync 3, 128;" ::: "memory");
    if (lane == 0 && (!helper || warp == 15)) {
      if (warp < 14) {
        if (warp == 12) x_load(NR);
        int slot = 0, par = 0;
#pragma unroll 1
        for (int n = NR; n < 36; n++) {
          mbar_wait(bars + 8 * (B_EA + slot), par);
          ring_part(warp - 12, n, slot);
          if (warp == 12 && n < 7) x_load(n + 1);
          if (++slot == NR) { slot = 0; par ^= 1; }
        }
      } else if (warp == 15) {
        const unsigned ep1 = ld_x1(&g_epoch[blockIdx.x * 8]) + 1;
        flag_wait(&g_cntX[helper ? 0 : 32 * j], ep1 * 16u);
        PROF_EV(22);
        mbar_expect_tx(bars + 8 * B_HX, U);
        bulk_load(sb + OFF_XB, g_X + (size_t)(helper ? 128 : kg * 8 + tn) * 8192, U, bars + 8 * B_HX);
        if (!helper) {
          flag_wait(&g_cntT[32 * j], ep1 * 16u);
          PROF_EV(23);
          mbar_expect_tx(bars + 8 * B_TL, U);
          tma3d(sb + OFF_T, &maps.t, bars + 8 * B_TL, 64 * j, 0, 2 * rb);
#pragma unroll 1
          for (int i = 0; i < 3; i++) { hint_wait(&g_cntP[32 * (rb * 8 + j) + i], ep1 * 8u); mbar_arrive(bars + 8 * (B_HP + i)); }
        }
      } else {
#pragma unroll 1
        for (int i = 4; i < 14; i++) asm volatile("prefetch.tensormap [%0];" ::"l"((const char*)&maps + i * 128) : "memory");
        PROF_EV(31);
        mbar_wait(bars + 8 * B_XS, 0);
#pragma unroll
        for (int h2 = 0; h2 < 2; h2++) {
          const int s0 = 2 * rb + h2, sg = (s0 & ~6) | ((s0 & 2) << 1) | ((s0 & 4) >> 1);
          asm volatile("cp.async.bulk.tensor.4d.global.shared::cta.bulk_group [%0, {%2, %3, %4, %5}], [%1];" ::"l"(&maps.xs), "r"(sb + OFF_XB + h2 * 8192),
                       "r"(0), "r"(sg), "r"(0), "r"(16 * j) : "memory");
          if (j == 0) {
#pragma unroll
            for (int c = 0; c < 2; c++)
              asm volatile("cp.async.bulk.global.shared::cta.bulk_group [%0], [%1], 256;" ::"l"(g_X + 128 * 8192 + c * 4096 + sg * 128),
                           "r"(sb + OFF_SP + h2 * 512 + c * 256) : "memory");
          }
        }
        bulk_done_signal(&g_cntX[32 * j]);
        PROF_EV(20);
#pragma unroll 1
        for (int t = 0; t < 8; t++) {
          const int i = t < 3 ? t + 1 : t < 6 ? t - 2 : 0;
          const int col = 64 * (2 * ((q4 + i) & 3) + ((t < 3 || t == 6) ? 1 - rank : rank));
          const uint32_t fb = bars + 8 * (B_FT + (t & 3)), dst = sb + (t & 3) * TB;
          mbar_wait(bars + 8 * (B_ET + (t == 0 ? 1 : t & 3)), t >> 2);
          mbar_expect_tx(fb, TB);
          tma2d(dst, &maps.d192, fb, col, f_full);
          tma2d(dst + 24576, &maps.d32, fb, col, f_half);
          tma2d(dst + 28672, &maps.ft, fb, col, 64 * j);
        }
      }
    }
  } else if (warp >= 8) {
    asm volatile("setmaxnreg.dec.sync.aligned.u32 104;");
    const int t = tid - 256, w = warp - 8;
    const uint32_t ep = ld_x1(&g_epoch[blockIdx.x * 8]);
    const uint32_t tag = (ep + 1) & 1;
    auto gate_rows = [&] {
      uint4 xv[8], gv[2];
#pragma unroll
      for (int i = 0; i < 4; i++) {
        const int r = 16 * j + 4 * w + i;
        const uint4* p = (const uint4*)(x + (size_t)(2 * rb + (r >> 6) + 32 * (r & 63)) * 512) + lane;
        xv[2 * i] = __ldg(p); xv[2 * i + 1] = __ldg(p + 32);
      }
      gv[0] = __ldg((const uint4*)gate_w + lane); gv[1] = __ldg((const uint4*)gate_w + lane + 32);
      {
        float z[4];
#pragma unroll
        for (int i = 0; i < 4; i++) {
          float a = 0.f;
#pragma unroll
          for (int hh = 0; hh < 2; hh++) {
            const uint4 u = xv[2 * i + hh], v = gv[hh];
            a = fmaf(bf_lo(u.x), bf_lo(v.x), a); a = fmaf(bf_hi(u.x), bf_hi(v.x), a);
            a = fmaf(bf_lo(u.y), bf_lo(v.y), a); a = fmaf(bf_hi(u.y), bf_hi(v.y), a);
            a = fmaf(bf_lo(u.z), bf_lo(v.z), a); a = fmaf(bf_hi(u.z), bf_hi(v.z), a);
            a = fmaf(bf_lo(u.w), bf_lo(v.w), a); a = fmaf(bf_hi(u.w), bf_hi(v.w), a);
          }
#pragma unroll
          for (int o = 16; o; o >>= 1) a += __shfl_xor_sync(0xffffffffu, a, o);
          z[i] = a;
        }
        if (lane < 4) {
          const float zz = lane == 0 ? z[0] : lane == 1 ? z[1] : lane == 2 ? z[2] : z[3];
          asm volatile("st.relaxed.gpu.global.f32 [%0], %1;" ::"l"(g_gate + rb * 128 + 16 * j + 4 * w + lane), "f"(tagf(1.0f / (1.0f + __expf(-zz)), tag)) : "memory");
        }
        if (t == 0) PROF_EV(18);
      }
      if (w == 0) {
        const int c = lane >> 4, jj = 16 * blockIdx.x + (lane & 15), jm = (2048 - jj) & 2047;
        const unsigned short* pr = (const unsigned short*)w_r + 256 * c;
        const unsigned short* pi = (const unsigned short*)w_i + 256 * c;
        const float wr = 0.25f * (bf_lo(__ldg(pr + jj * 257)) + bf_lo(__ldg(pr + jm * 257)));
        const float wi = 0.25f * (bf_lo(__ldg(pi + jj * 257)) - bf_lo(__ldg(pi + jm * 257)));
        st_u2(g_Wh + c * 2048 + jj, c ? pack_bf16(-wi, wr) : pack_bf16(wr, wi), tag);
        __syncwarp();
        if (lane == 0) hint_add(&g_cntW[0]);
      }
    };
    {
      const int g = lane >> 2, q = lane & 3;
      uint32_t wf[32];
      if (!helper) {
        gate_rows();
        asm volatile("bar.sync 4, 256;" ::: "memory");
        const uint32_t wa = sb + OFF_T + w * (3072 + 4) + q * 48 + g * 2;
        mbar_wait(bars + 8 * (B_FX + WAFTER), 0);
        if (t == 0) PROF_EV(32);
        __nanosleep(WPACE * w);
#pragma unroll
        for (int ri = 0; ri < 2; ri++) {
          if (lane == 0) {
            mbar_expect_tx(bars + 8 * (B_WR + w), 3072);
            tma4d(sb + OFF_T + w * 3072, ri ? &maps.wi : &maps.wr, bars + 8 * (B_WR + w), 16 * kg, 0, 2 * w, tn);
          }
          mbar_wait(bars + 8 * (B_WR + w), ri);
#pragma unroll
          for (int n2 = 0; n2 < 4; n2++) {
            uint32_t v[8];
#pragma unroll
            for (int i = 0; i < 8; i++)
              asm volatile("ld.shared.u16 %0, [%1];" : "=r"(v[i]) : "r"(wa + (2 * n2 + ((i >> 1) & 1)) * 192 + (i & 1) * (1536 + 2) + (i >> 2) * 16) : "memory");
#pragma unroll
            for (int i = 0; i < 8; i++) {
              uint32_t& d = wf[(i >> 2) * 16 + 4 * n2 + (i & 3)];
              d = ri ? d | (v[i] << 16) : v[i];
              asm volatile("" : "+r"(d)::"memory");
            }
          }
          __syncwarp();
        }
        asm volatile("bar.sync 1, 128;" ::: "memory");
        if (t == 0) PROF_EV(11);
      } else {
        asm volatile("bar.sync 4, 256;" ::: "memory");
        hint_wait(&g_cntW[0], (ep + 1) * 128u);
        const uint32_t t0 = (uint32_t)clock();
#pragma unroll 1
        for (;;) {
          uint32_t bad = 0;
#pragma unroll
          for (int i = 0; i < 32; i++) {
            const float2 v = ld_x2((const float2*)g_Wh + (i >> 4) * 2048 + 16 * w + g + 8 * (i & 1) + 64 * q + ((i >> 1) & 7) * 256);
            wf[i] = __float_as_uint(v.x); bad |= __float_as_uint(v.y) ^ tag;
          }
          if (!__any_sync(0xffffffffu, bad & 1)) break;
          spin_guard(t0);
        }
        if (t == 0) PROF_EV(11);
      }
      if (t == 0) { mbar_expect_tx(bars + 8 * B_W, 8192); bulk_load(sb + OFF_D, g_DT.v, 8192, bars + 8 * B_W); }
      mbar_wait(bars + 8 * B_W, 0);
      mbar_wait(bars + 8 * B_HX, 0);
      if (t == 0) PROF_EV(12);
      const uint32_t dd = (sb & 0x3FFFF) >> 4;
      const uint64_t dF = d128((dd + (OFF_D >> 4)) | (512u << 16)), dI = d128((dd + (OFF_D >> 4)) | (1u << 16)), dA = d128((dd + (OFF_XB >> 4)) | (512u << 16));
      float az[32];
      const int zero = blockIdx.x >> 16;
      uint32_t pf[32];
#pragma unroll
      for (int mt = 0; mt < 2; mt++) {
        wg_fence();
        if (mt == 0) mma_ss64<0, 3, 0>(az, dA, dF);
        else mma_ss64<0, 3, 2>(az, dA + 512, dF, zero);
#pragma unroll
        for (int k = 1; k < 4; k++) mma_ss64<0, 3, 1>(az, dA + (mt * 512 + k * 128), dF + k * 128);
        wg_commit();
        wg_wait<0>();
        fence_regs<0, 32>(az);
#pragma unroll
        for (int i = 0; i < 16; i++) {
          const float wr = bf_lo(wf[16 * mt + i]), wi = bf_hi(wf[16 * mt + i]);
          pf[16 * mt + i] = pack_pin(fmaf(az[2 * i], wr, -az[2 * i + 1] * wi), fmaf(az[2 * i], wi, az[2 * i + 1] * wr));
        }
      }
      if (t == 0) PROF_EV(16);
#pragma unroll
      for (int mt = 0; mt < 2; mt++) {
        wg_fence();
        mma_rs64<0, 0, 2>(az, pf[16 * mt], pf[16 * mt + 1], pf[16 * mt + 2], pf[16 * mt + 3], dI, mt ? (int)helper : zero);
#pragma unroll
        for (int k = 1; k < 4; k++) mma_rs64<0, 0, 1>(az, pf[16 * mt + 4 * k], pf[16 * mt + 4 * k + 1], pf[16 * mt + 4 * k + 2], pf[16 * mt + 4 * k + 3], dI + k * 2);
        wg_commit();
        wg_wait<0>();
        fence_regs<0, 32>(az);
        if (!helper) {
          const int m = lane >> 3, r = lane & 7;
          const int sl = 2 * (m >> 1) + ((r >> 1) & 1) + 4 * (r >> 2);
          const uint32_t a0 = sb + OFF_XB + (2 * w + (m & 1)) * 2048 + sl * 64 + (((mt * 2 + (r & 1)) ^ (sl >> 1)) << 4);
#pragma unroll
          for (int i = 0; i < 4; i++)
            stsm4t(a0 + i * 512, pack_bf16(az[8 * i], az[8 * i + 1]), pack_bf16(az[8 * i + 2], az[8 * i + 3]), pack_bf16(az[8 * i + 4], az[8 * i + 5]),
                   pack_bf16(az[8 * i + 6], az[8 * i + 7]));
        }
      }
      if (helper) {
#pragma unroll
        for (int i = 0; i < 16; i++) {
          const int n = i >> 1, s0 = 8 * (n >> 1) + 2 * (n & 1) + (q & 1) + 4 * (q >> 1);
          if ((n & 1) == (int)(blockIdx.x & 1)) st_u2(g_Ts + s0 * 64 + 16 * w + g + 8 * (i & 1), pack_bf16(az[2 * i], az[2 * i + 1]), tag);
        }
        __syncwarp();
        if (lane == 0) hint_add(&g_cntH[0]);
        if (t == 0) { g_epoch[blockIdx.x * 8] = ep + 1; PROF_EV(13); }
      } else {
        asm volatile("fence.proxy.async.shared::cta;" ::: "memory");
        asm volatile("bar.sync 1, 128;" ::: "memory");
        if (t == 0) {
          PROF_EV(17);
          asm volatile("cp.async.bulk.tensor.3d.global.shared::cta.bulk_group [%0, {%2, %3, %4}], [%1];" ::"l"(&maps.ts), "r"(sb + OFF_XB),
                       "r"(32 * kg), "r"(0), "r"(8 * tn) : "memory");
          bulk_done_signal(&g_cntT[32 * j]);
          PROF_EV(13);
        }
        __syncwarp();
        if (j == 0) {
          hint_wait(&g_cntH[0], (ep + 1) * 8u);
          const uint32_t t0 = (uint32_t)clock();
          float2 v;
          do { v = ld_x2((const float2*)g_Ts + 2 * rb * 64 + t); spin_guard(t0); } while (__any_sync(0xffffffffu, (__float_as_uint(v.y) ^ tag) & 1));
          mbar_wait(bars + 8 * B_TL, 0);
          const uint32_t u = __float_as_uint(v.x);
          *(uint16_t*)(smem + OFF_T + t * 128 + ((t & 7) << 4)) = (uint16_t)u;
          *(uint16_t*)(smem + OFF_T + t * 128 + (((t & 7) ^ 1) << 4)) = (uint16_t)(u >> 16);
          asm volatile("fence.proxy.async.shared::cta;" ::: "memory");
          __syncwarp();
          if (lane == 0) mbar_arrive(bars + 8 * B_T);
        }
      }
    }
  } else {
    asm volatile("setmaxnreg.inc.sync.aligned.u32 192;");
    if (tid == 0) PROF_EV(33);
    if (!helper) {
      const int wg = warp >> 2, w = warp & 3, g = lane >> 2, q = lane & 3;
      const bool elect = (tid & 127) == 0;
      const uint32_t ep = ld_x1(&g_epoch[blockIdx.x * 8]);
      float c1[64], cA[64], c2[64], ci[64], ct[64];
      const int zero = blockIdx.x >> 16;
      uint32_t h[56], yf[16];
      const uint32_t d0 = (sb & 0x3FFFF) >> 4;
      const uint32_t dK = d0 | (1u << 16), dN = d0 | (512u << 16), dM = d0 | (256u << 16);
      const uint32_t dX = dK + wg * 512;
      constexpr uint32_t RING = OFF_RING >> 4;
      auto waitA = [&](int n) { mbar_wait(bars + 8 * (B_FA + rslot(n)), rpar(n)); };
      auto freeA = [&](int n) { if (elect) mbar_arrive(bars + 8 * (B_EA + rslot(n))); };
      auto nop = [](int) {};

#pragma unroll
      for (int kb = 0; kb < 8; kb++) {
        if (kb == 0) asm volatile("bar.sync 0, 384;" ::: "memory");
        mbar_wait(bars + 8 * (B_FX + kb), 0); waitA(kb);
        wg_fence();
        const uint64_t dx = d128(dX + kb * 1024), df = d128(dK + RING + rslot(kb) * 1024), dm = d64(dM + RING + 512 + rslot(kb) * 1024);
        if (kb == 0) { mma_ss64<0, 0, 0>(c1, df, dx); mma_ss64<32, 1, 0>(c1, dx, dm); }
        else { mma_ss64<0, 0, 1>(c1, df, dx); mma_ss64<32, 1, 1>(c1, dx, dm); wg_commit(); wg_wait<1>(); freeA(kb - 1); }
#pragma unroll
        for (int k = 1; k < 4; k++) {
          mma_ss64<0, 0, 1>(c1, df + k * 2, dx + k * 2);
          mma_ss64<32, 1, 1>(c1, dx + k * 2, dm + k * 64);
        }
        wg_commit();
        if (kb == 0 && tid == 0) PROF_EV(1);
      }
      auto ffn_step = [&](auto first, float (&acc)[64], int n, int kb, auto done, auto work) {
        waitA(n);
        wg_fence();
        const uint64_t dx = d128(dX + kb * 1024), db = d128(dN + RING + rslot(n) * 1024);
        mma_ss128<0, 1, decltype(first)::value>(acc, dx, db, zero);
        wg_commit();
        wg_wait<1>();
        done();
#pragma unroll
        for (int k = 1; k < 4; k++) { mma_ss128<0, 1, 1>(acc, dx + k * 2, db + k * 128); work(k - 1); }
        wg_commit();
        work(3);
      };
      const uint32_t tag = (ep + 1) & 1;
      float hm[16];
      ffn_step(IC<0>(), c2, 8, 0, [&] { freeA(7); fence_regs<0, 64>(c1); }, [&](int i) {
#pragma unroll
        for (int e = 4 * i; e < 4 * i + 4; e++) { yf[e] = pack_pin(c1[2 * e], c1[2 * e + 1]); hm[e] = fmaxf(c1[32 + e], 0.f) * c1[48 + e]; }
      });
      fence_regs<0, 16>(hm);
      if (tid == 0) PROF_EV(2);
      {
        waitA(9); waitA(10);
        const uint64_t de = d128(dN + RING + (wg ? rslot(10) : rslot(9)) * 1024);
        wg_fence();
        mma_rs128<0, 1, 0>(cA, yf[0], yf[1], yf[2], yf[3], de);
        wg_commit();
        wg_wait<1>();
        freeA(8);
#pragma unroll
        for (int k = 1; k < 4; k++) mma_rs128<0, 1, 1>(cA, yf[4 * k], yf[4 * k + 1], yf[4 * k + 2], yf[4 * k + 3], de + k * 128);
        wg_commit();
      }
      {
        const int s0 = 2 * rb + wg, kr = 2 * ((s0 & 1) | ((s0 & 4) >> 1));
        const int m = lane >> 3, r = lane & 7;
        const uint32_t a0 = sb + OFF_XB + wg * 8192 + (((w >> 1) * 8 + (m >> 1)) * 2 + (w & 1)) * 256 + (m & 1) * 128 + ((r ^ (kr + (m & 1))) << 4);
        ffn_step(IC<1>(), c2, 11, 1, [&] { freeA(9); freeA(10); fence_regs<0, 64>(cA); }, [&](int i) {
          stsm4t(a0 + i * 1024, pack_bf16(cA[8 * i] - cA[34 + 8 * i], cA[8 * i + 1] - cA[35 + 8 * i]),
                 pack_bf16(cA[32 + 8 * i] + cA[8 * i + 2], cA[33 + 8 * i] + cA[8 * i + 3]),
                 pack_bf16(cA[8 * i + 4] - cA[38 + 8 * i], cA[8 * i + 5] - cA[39 + 8 * i]),
                 pack_bf16(cA[36 + 8 * i] + cA[8 * i + 6], cA[37 + 8 * i] + cA[8 * i + 7]));
        });
        if (j == 0 && w == 0 && g == 0) {
#pragma unroll
          for (int n = 0; n < 8; n++)
#pragma unroll
            for (int ce = 0; ce < 4; ce++)
              *(uint32_t*)(smem + OFF_SP + wg * 512 + ce * 128 + ((n ^ (kr + (ce & 1))) << 4) + 4 * q) =
                  pack_bf16(cA[(ce & 1) * 32 + 4 * n + (ce & 2)], cA[(ce & 1) * 32 + 4 * n + (ce & 2) + 1]);
        }
        asm volatile("fence.proxy.async.shared::cta;" ::: "memory");
        __syncwarp();
        if (lane == 0) mbar_arrive(bars + 8 * B_XS);
        if (tid == 0) PROF_EV(3);
      }
      const float* gp = g_gate + rb * 128 + wg * 64 + w * 16 + g;
      uint32_t gb0 = ld_x1(gp), gb1 = ld_x1(gp + 8);
#pragma unroll
      for (int kb = 2; kb < 7; kb++) ffn_step(IC<1>(), c2, 10 + kb, kb, [&] { freeA(9 + kb); }, nop);
      {
        const uint32_t t0 = (uint32_t)clock();
        while (__any_sync(0xffffffffu, ((gb0 ^ tag) | (gb1 ^ tag)) & 1)) { gb0 = ld_x1(gp); gb1 = ld_x1(gp + 8); spin_guard(t0); }
      }
      const float g0 = __uint_as_float(gb0 & ~1u), g1 = __uint_as_float(gb1 & ~1u);
      const float o0 = 1.0f - g0, o1 = 1.0f - g1;
      uint32_t hp[8];
      ffn_step(IC<1>(), c2, 17, 7, [&] { freeA(16); }, [&](int i) {
        hp[2 * i] = pack_pin(hm[4 * i] * o0, hm[4 * i + 1] * o0); hp[2 * i + 1] = pack_pin(hm[4 * i + 2] * o1, hm[4 * i + 3] * o1);
      });
      auto glu = [&](float (&acc)[64], int ho, int i0, int i1) {
#pragma unroll
        for (int i = i0; i < i1; i++) {
          const float o = (i & 1) ? o1 : o0;
          h[ho + i] = pack_pin(fmaxf(acc[2 * i], 0.f) * acc[32 + 2 * i] * o, fmaxf(acc[2 * i + 1], 0.f) * acc[33 + 2 * i] * o);
        }
      };
      ffn_step(IC<2>(), cA, 18, 0, [&] { freeA(17); fence_regs<0, 64>(c2); }, [&](int i) { glu(c2, 0, 2 * i, 2 * i + 2); });
      if (tid == 0) PROF_EV(4);
      ffn_step(IC<1>(), cA, 19, 1, [&] { freeA(18); }, [&](int i) { glu(c2, 0, 8 + 2 * i, 10 + 2 * i); });
#pragma unroll
      for (int kb = 2; kb < 8; kb++) ffn_step(IC<1>(), cA, 18 + kb, kb, [&] { freeA(17 + kb); }, nop);
      ffn_step(IC<2>(), c2, 26, 0, [&] { freeA(25); fence_regs<0, 64>(cA); }, [&](int i) { glu(cA, 16, 2 * i, 2 * i + 2); });
      if (tid == 0) PROF_EV(5);
      ffn_step(IC<1>(), c2, 27, 1, [&] { freeA(26); }, [&](int i) { glu(cA, 16, 8 + 2 * i, 10 + 2 * i); });
#pragma unroll
      for (int kb = 2; kb < 8; kb++)
        ffn_step(IC<1>(), c2, 26 + kb, kb, [&] {
          if (kb < 7) freeA(25 + kb);
          if (kb >= 3 && (kb & 1) && elect) mbar_arrive(bars + 8 * (B_ET + ((kb - 3) >> 1)));
        }, nop);
      wg_wait<0>();
      if (elect) mbar_arrive(bars + 8 * (B_ET + 3));
      fence_regs<0, 64>(c2);
      glu(c2, 32, 0, 16);
#pragma unroll
      for (int i = 0; i < 8; i++) h[48 + i] = hp[i] ^ zero;
      if (wg) waitA(35); else waitA(34);
      if (tid == 0) PROF_EV(6);
      mbar_wait(bars + 8 * (j == 0 ? B_T : B_TL), 0);
      if (tid == 0) PROF_EV(7);
      wg_fence();
      {
        const uint64_t dt = d128(dN + (OFF_T >> 4) + wg * 512), de = d128(dK + RING + (wg ? rslot(35) : rslot(34)) * 1024);
        mma_ss64<0, 1, 0>(ci, de, dt);
        mma_ss64<32, 1, 0>(ci, de + 512, dt);
#pragma unroll
        for (int k = 1; k < 4; k++) {
          mma_ss64<0, 1, 1>(ci, de + k * 2, dt + k * 128);
          mma_ss64<32, 1, 1>(ci, de + (512 + k * 2), dt + k * 128);
        }
      }
      wg_commit();

      auto head = [&](auto off, int t) {
        constexpr int O = decltype(off)::value;
        mbar_wait(bars + 8 * (B_FT + (t & 3)), t >> 2);
        const uint64_t db = d128(dN + (t & 3) * (TB >> 4));
        wg_fence();
        mma_rs64<O, 1, 0>(ct, h[0], h[1], h[2], h[3], db);
#pragma unroll
        for (int k = 1; k < 6; k++) mma_rs64<O, 1, 1>(ct, h[4 * k], h[4 * k + 1], h[4 * k + 2], h[4 * k + 3], db + k * 128);
        wg_commit();
        wg_wait<1>();
      };
      auto rest = [&](auto off, int t) {
        constexpr int O = decltype(off)::value;
        const uint64_t db = d128(dN + (t & 3) * (TB >> 4));
        wg_fence();
#pragma unroll
        for (int k = 6; k < 14; k++) mma_rs64<O, 1, 1>(ct, h[4 * k], h[4 * k + 1], h[4 * k + 2], h[4 * k + 3], db + k * 128);
#pragma unroll
        for (int k = 0; k < 4; k++) mma_rs64<O, 1, 1>(ct, yf[4 * k], yf[4 * k + 1], yf[4 * k + 2], yf[4 * k + 3], db + (14 + k) * 128);
        wg_commit();
      };
      auto freeT = [&](int t) { if (elect) mbar_arrive(bars + 8 * (B_ET + t)); };
      const uint32_t peerZ = mapa(sb + OFF_Z + tid * 16, rank ^ 1), peerB = mapa(bars + 8 * B_Z, rank ^ 1);
      auto send_peer = [&](auto off, int z) {
        constexpr int O = decltype(off)::value;
        fence_regs<O, 32>(ct);
#pragma unroll
        for (int i = 0; i < 4; i++)
          asm volatile("st.async.weak.shared::cluster.mbarrier::complete_tx::bytes.v4.b32 [%0], {%1,%2,%3,%4}, [%5];" ::"r"(peerZ + z * U + i * 4096),
                       "r"(pack_bf16(ct[O + 8 * i], ct[O + 8 * i + 1])), "r"(pack_bf16(ct[O + 8 * i + 2], ct[O + 8 * i + 3])),
                       "r"(pack_bf16(ct[O + 8 * i + 4], ct[O + 8 * i + 5])), "r"(pack_bf16(ct[O + 8 * i + 6], ct[O + 8 * i + 7])), "r"(peerB + 8 * z) : "memory");
      };
      auto send_grid = [&](auto off, int z) {
        constexpr int O = decltype(off)::value;
        fence_regs<O, 32>(ct);
        mbar_wait(bars + 8 * (B_Z + z), 0);
        uint4* dst = g_part + (size_t)((rb * 8 + 2 * ((q4 + z + 1) & 3) + rank) * 3 + z) * 1024 + tid;
#pragma unroll
        for (int i = 0; i < 4; i++) {
          const uint4 p = *(const uint4*)(smem + OFF_Z + z * U + i * 4096 + tid * 16);
          st_x4(dst + i * 256, (pack_bf16(ct[O + 8 * i] + bf_lo(p.x), ct[O + 8 * i + 1] + bf_hi(p.x)) & ~1u) | tag,
                pack_bf16(ct[O + 8 * i + 2] + bf_lo(p.y), ct[O + 8 * i + 3] + bf_hi(p.y)),
                pack_bf16(ct[O + 8 * i + 4] + bf_lo(p.z), ct[O + 8 * i + 5] + bf_hi(p.z)),
                pack_bf16(ct[O + 8 * i + 6] + bf_lo(p.w), ct[O + 8 * i + 7] + bf_hi(p.w)));
        }
        __syncwarp();
        if (lane == 0) hint_add(&g_cntP[32 * (rb * 8 + 2 * ((q4 + z + 1) & 3) + rank) + z]);
      };
      asm volatile("barrier.cluster.wait.aligned;" ::: "memory");
      head(IC<0>(), 0);
      if (elect) asm volatile("mbarrier.arrive.shared::cluster.b64 _, [%0];" ::"r"(mapa(bars + 8 * B_RDY, rank ^ 1)) : "memory");
      fence_regs<0, 64>(ci);
#pragma unroll
      for (int i = 0; i < 16; i++) {
        const float gg = ((i & 1) ? g1 : g0) * (2.0f / (2048.0f * 512.0f));
        if (i & 2) yf[i] = pack_pin((ci[2 * i] - ci[28 + 2 * i]) * gg, (ci[2 * i + 1] - ci[29 + 2 * i]) * gg);
        else yf[i] = pack_pin((ci[2 * i] + ci[36 + 2 * i]) * gg, (ci[2 * i + 1] + ci[37 + 2 * i]) * gg);
      }
      rest(IC<0>(), 0);
      if (tid == 0) PROF_EV(8);
      head(IC<32>(), 1); freeT(0); mbar_wait(bars + 8 * B_RDY, 0); send_peer(IC<0>(), 0); rest(IC<32>(), 1);
      head(IC<0>(), 2); freeT(1); send_peer(IC<32>(), 1); rest(IC<0>(), 2);
      head(IC<32>(), 3); freeT(2); send_peer(IC<0>(), 2); rest(IC<32>(), 3);
      head(IC<0>(), 4); freeT(3); send_grid(IC<32>(), 0); rest(IC<0>(), 4);
      head(IC<32>(), 5); send_grid(IC<0>(), 1); rest(IC<32>(), 5);
      head(IC<0>(), 6); send_grid(IC<32>(), 2); rest(IC<0>(), 6);
      head(IC<32>(), 7); send_peer(IC<0>(), 3);
      {
        const uint4* src = g_part + (size_t)(rb * 8 + j) * 3 * 1024 + tid;
        uint4 pv[12];
        mbar_wait(bars + 8 * (B_HP + 1), 0);
#pragma unroll
        for (int i = 0; i < 8; i++) pv[i] = ld_x4(src + i * 256);
        rest(IC<32>(), 7);
        if (tid == 0) PROF_EV(9);
        mbar_wait(bars + 8 * (B_HP + 2), 0);
        if (tid == 0) PROF_EV(24);
#pragma unroll
        for (int i = 8; i < 12; i++) pv[i] = ld_x4(src + i * 256);
        const uint32_t t0 = (uint32_t)clock();
        for (;;) {
          uint32_t bad = 0;
#pragma unroll
          for (int i = 0; i < 12; i++) bad |= pv[i].x ^ tag;
          if (!__any_sync(0xffffffffu, bad & 1)) break;
#pragma unroll
          for (int i = 0; i < 12; i++) pv[i] = ld_x4(src + i * 256);
          spin_guard(t0);
        }
        if (tid == 0) PROF_EV(14);
        float sum[32];
#pragma unroll
        for (int i = 0; i < 4; i++) {
          const uint32_t a[4] = {pv[i].x & ~1u, pv[i].y, pv[i].z, pv[i].w}, b[4] = {pv[4 + i].x & ~1u, pv[4 + i].y, pv[4 + i].z, pv[4 + i].w},
                         c[4] = {pv[8 + i].x & ~1u, pv[8 + i].y, pv[8 + i].z, pv[8 + i].w};
#pragma unroll
          for (int e = 0; e < 4; e++) {
            sum[8 * i + 2 * e] = bf_lo(a[e]) + bf_lo(b[e]) + bf_lo(c[e]);
            sum[8 * i + 2 * e + 1] = bf_hi(a[e]) + bf_hi(b[e]) + bf_hi(c[e]);
          }
        }
        mbar_wait(bars + 8 * (B_Z + 3), 0);
#pragma unroll
        for (int i = 0; i < 4; i++) {
          const uint4 p = *(const uint4*)(smem + OFF_Z + 3 * U + i * 4096 + tid * 16);
          const uint32_t a[4] = {p.x, p.y, p.z, p.w};
#pragma unroll
          for (int e = 0; e < 4; e++) { sum[8 * i + 2 * e] += bf_lo(a[e]); sum[8 * i + 2 * e + 1] += bf_hi(a[e]); }
        }
        wg_wait<0>();
        fence_regs<32, 32>(ct);
#pragma unroll
        for (int i = 0; i < 32; i++) sum[i] += ct[32 + i];
        const uint32_t stg = sb + OFF_T + warp * 2048;
        const int mr = (lane & 7) + ((lane >> 3) & 1) * 8, mc = lane >> 4;
#pragma unroll
        for (int i = 0; i < 4; i++) {
          const uint32_t a = stg + mr * 128 + (((2 * i + mc) ^ (mr & 7)) << 4);
          asm volatile("stmatrix.sync.aligned.m8n8.x4.shared.b16 [%0], {%1,%2,%3,%4};" ::"r"(a), "r"(pack_bf16(sum[8 * i], sum[8 * i + 1])),
                       "r"(pack_bf16(sum[8 * i + 2], sum[8 * i + 3])), "r"(pack_bf16(sum[8 * i + 4], sum[8 * i + 5])),
                       "r"(pack_bf16(sum[8 * i + 6], sum[8 * i + 7])) : "memory");
        }
        __syncwarp();
#pragma unroll
        for (int i = 0; i < 4; i++) {
          const int r = 4 * i + (lane >> 3), c = lane & 7;
          const uint4 v = *(const uint4*)(smem + OFF_T + warp * 2048 + r * 128 + ((c ^ (r & 7)) << 4));
          *(uint4*)(out + (size_t)(2 * rb + wg + 32 * (16 * w + r)) * 512 + 64 * j + 8 * c) = v;
        }
      }
      if (tid == 0) { g_epoch[blockIdx.x * 8] = ep + 1; PROF_EV(15); PROF_CK(41); }
    }
  }
}

typedef CUresult (*EncodeFn)(CUtensorMap*, CUtensorMapDataType, cuuint32_t, void*, const cuuint64_t*, const cuuint64_t*, const cuuint32_t*,
                             const cuuint32_t*, CUtensorMapInterleave, CUtensorMapSwizzle, CUtensorMapL2promotion, CUtensorMapFloatOOBfill);

static void encode(EncodeFn f, CUtensorMap* m, const void* base, int rank, const cuuint64_t* dims, const cuuint64_t* strides, const cuuint32_t* box,
                   CUtensorMapSwizzle sw) {
  cuuint32_t es[5] = {1, 1, 1, 1, 1};
  f(m, CU_TENSOR_MAP_DATA_TYPE_BFLOAT16, rank, (void*)base, dims, strides, box, es, CU_TENSOR_MAP_INTERLEAVE_NONE, sw,
    CU_TENSOR_MAP_L2_PROMOTION_L2_128B, CU_TENSOR_MAP_FLOAT_OOB_FILL_NONE);
}

extern "C" void kernel_launch(void* const* d_in, const int* in_sizes, int n_in, void* d_out, int out_size) {
  (void)in_sizes; (void)n_in; (void)out_size;
  const __nv_bfloat16* x = (const __nv_bfloat16*)d_in[0];
  const __nv_bfloat16* w_r = (const __nv_bfloat16*)d_in[1];
  const __nv_bfloat16* w_i = (const __nv_bfloat16*)d_in[2];
  const __nv_bfloat16* Wg = (const __nv_bfloat16*)d_in[4];
  const __nv_bfloat16* Wu = (const __nv_bfloat16*)d_in[5];
  const __nv_bfloat16* Wd = (const __nv_bfloat16*)d_in[6];
  const __nv_bfloat16* gw = (const __nv_bfloat16*)d_in[7];

  void* fp = nullptr; cudaDriverEntryPointQueryResult qr;
  cudaGetDriverEntryPoint("cuTensorMapEncodeTiled", &fp, cudaEnableDefault, &qr);
  EncodeFn enc = (EncodeFn)fp;
  void *pFT, *pET, *pX, *pT;
  cudaGetSymbolAddress(&pX, g_X); cudaGetSymbolAddress(&pT, g_T);
  cudaGetSymbolAddress(&pFT, g_FT); cudaGetSymbolAddress(&pET, g_ET);

  Maps mp;
  const CUtensorMapSwizzle S128 = CU_TENSOR_MAP_SWIZZLE_128B, S64 = CU_TENSOR_MAP_SWIZZLE_64B;
  { cuuint64_t d[3] = {512, 64, 32}, s[2] = {32768, 1024}; cuuint32_t b[3] = {64, 64, 2}; encode(enc, &mp.x, x, 3, d, s, b, S128); }
  { cuuint64_t d[2] = {512, 512}, s[1] = {1024}; cuuint32_t b[2] = {64, 64}; encode(enc, &mp.ft, pFT, 2, d, s, b, S128); }
  { cuuint64_t d[4] = {128, 32, 2, 129}, s[3] = {256, 8192, 16384}; cuuint32_t b[4] = {128, 1, 2, 16}; encode(enc, &mp.xs, pX, 4, d, s, b, CU_TENSOR_MAP_SWIZZLE_NONE); }
  { cuuint64_t d[3] = {512, 32, 64}, s[2] = {65536, 1024}; cuuint32_t b[3] = {32, 32, 8}; encode(enc, &mp.ts, pT, 3, d, s, b, S64); }
  { cuuint64_t d[3] = {512, 64, 32}, s[2] = {1024, 65536}; cuuint32_t b[3] = {64, 64, 2}; encode(enc, &mp.t, pT, 3, d, s, b, S128); }
  { cuuint64_t d[4] = {64, 64, 2, 32}, s[3] = {8192, 128, 256}; cuuint32_t b[4] = {64, 64, 2, 1}; encode(enc, &mp.e, pET, 4, d, s, b, S128); }
  { cuuint64_t d[2] = {1792, 512}, s[1] = {3584}; cuuint32_t b[2] = {64, 64}, b2[2] = {32, 64};
    encode(enc, &mp.g64, Wg, 2, d, s, b, S128); encode(enc, &mp.u64, Wu, 2, d, s, b, S128);
    encode(enc, &mp.g32, Wg, 2, d, s, b2, S64); encode(enc, &mp.u32, Wu, 2, d, s, b2, S64); }
  { cuuint64_t d[2] = {512, 1792}, s[1] = {1024}; cuuint32_t b[2] = {64, 192}, b2[2] = {64, 32};
    encode(enc, &mp.d192, Wd, 2, d, s, b, S128); encode(enc, &mp.d32, Wd, 2, d, s, b2, S128); }

  { cuuint64_t d[4] = {264, 32, 8, 8}, s[3] = {32896, 512, 4112}; cuuint32_t b[4] = {24, 32, 2, 1};
    encode(enc, &mp.wr, w_r, 4, d, s, b, CU_TENSOR_MAP_SWIZZLE_NONE); encode(enc, &mp.wi, w_i, 4, d, s, b, CU_TENSOR_MAP_SWIZZLE_NONE); }

  cudaFuncSetAttribute(fused_kernel, cudaFuncAttributeMaxDynamicSharedMemorySize, SMEM_BYTES);
  fused_kernel<<<NCTA, 512, SMEM_BYTES>>>(mp, x, w_r, w_i, gw, (__nv_bfloat16*)d_out);
}
```

```cpp
#include <cuda_runtime.h>
#include <cuda_bf16.h>
#include <cuda.h>
#include <stdint.h>

namespace tbl {
constexpr double PI = 3.14159265358979323846264338327950288;
constexpr double sin_s(double x) { double t = x, s = x; for (int n = 1; n < 12; n++) { t *= -x * x / ((2 * n) * (2 * n + 1)); s += t; } return s; }
constexpr double cos_s(double x) { double t = 1, s = 1; for (int n = 1; n < 12; n++) { t *= -x * x / ((2 * n - 1) * (2 * n)); s += t; } return s; }
constexpr double cos2048(int m) {
  m &= 2047; if (m > 1024) m = 2048 - m;
  bool neg = false; if (m > 512) { m = 1024 - m; neg = true; }
  double v = (m <= 256) ? cos_s(2 * PI * m / 2048) : sin_s(2 * PI * (512 - m) / 2048);
  return neg ? -v : v;
}
constexpr uint16_t to_bf16(double v) {
  if (v == 0) return 0;
  uint16_t s = 0; if (v < 0) { s = 0x8000; v = -v; }
  int e = 0; while (v >= 2) { v /= 2; e++; } while (v < 1) { v *= 2; e--; }
  double m = (v - 1) * 128; int mi = (int)m; double fr = m - mi;
  if (fr > 0.5 || (fr == 0.5 && (mi & 1))) mi++;
  if (mi == 128) { mi = 0; e++; }
  return (uint16_t)(s | ((e + 127) << 7) | mi);
}
struct CosT { uint16_t v[2048]; constexpr CosT() : v() { for (int i = 0; i < 2048; i++) v[i] = to_bf16(cos2048(i)); } };
struct alignas(1024) FT {
  uint16_t v[512 * 512];
  constexpr FT() : v() {
    CosT c;
    for (int r = 0; r < 512; r++) {
      int k = (r >> 4) * 8 + (r & 7), e = (r >> 3) & 1;
      int mul = 4 * k, add = e ? 512 : 0;
      if (k == 0 && e == 1) { mul = 1024; add = 0; }
      for (int d = 0; d < 512; d++) v[r * 512 + d] = c.v[(d * mul + add) & 2047];
    }
  }
};
struct alignas(1024) ET {
  uint16_t v[2048 * 128];
  constexpr ET() : v() {
    CosT c;
    for (int s = 0; s < 2048; s++)
      for (int j = 0; j < 64; j++) { v[s * 128 + j] = c.v[(s * j) & 2047]; v[s * 128 + 64 + j] = c.v[(s * j + 512) & 2047]; }
  }
};
struct alignas(1024) DT {
  uint16_t v[64 * 64];
  constexpr DT() : v() {
    CosT c;
    for (int r = 0; r < 64; r++)
      for (int n = 0; n < 64; n++) {
        const int sg = r >> 1, s0 = (sg & ~6) | ((sg & 2) << 1) | ((sg & 4) >> 1), e = r & 1, f = n & 1;
        const int m = 64 * s0 * (n >> 1) + (e == f ? 0 : e ? -512 : 512);
        v[r * 64 + (((n >> 3) ^ (r & 7)) << 3) + (n & 7)] = c.v[m & 2047];
      }
  }
};
}

__device__ constexpr tbl::FT g_FT = tbl::FT();
__device__ constexpr tbl::ET g_ET = tbl::ET();
__device__ constexpr tbl::DT g_DT = tbl::DT();

__device__ __align__(1024) uint16_t g_X[129 * 8192];
__device__ __align__(1024) uint16_t g_T[32 * 64 * 512];
__device__ __align__(1024) uint2 g_Ts[32 * 64];
__device__ __align__(1024) uint4 g_part[128 * 3 * 1024];
__device__ __align__(16) float g_gate[16 * 128];
__device__ __align__(16) uint2 g_Wh[2 * 2048];
__device__ unsigned g_epoch[132 * 8];
__device__ unsigned g_cntX[8 * 32], g_cntT[8 * 32], g_cntP[128 * 32], g_cntW[32], g_cntH[32];
#define PROF_EV(i) do {} while (0)
#define PROF_CK(i) do {} while (0)

__device__ __forceinline__ uint32_t smem_u32(const void* p) { return (uint32_t)__cvta_generic_to_shared(p); }
__device__ __forceinline__ void mbar_init(uint32_t bar, uint32_t cnt) { asm volatile("mbarrier.init.shared::cta.b64 [%0], %1;" ::"r"(bar), "r"(cnt)); }
__device__ __forceinline__ void mbar_expect_tx(uint32_t bar, uint32_t bytes) { asm volatile("mbarrier.arrive.expect_tx.shared::cta.b64 _, [%0], %1;" ::"r"(bar), "r"(bytes) : "memory"); }
__device__ __forceinline__ void mbar_arrive(uint32_t bar) { asm volatile("mbarrier.arrive.shared::cta.b64 _, [%0];" ::"r"(bar) : "memory"); }
__device__ __forceinline__ void mbar_wait(uint32_t bar, uint32_t parity) {
  asm volatile(
      "{\n.reg .pred p;\n.reg .u32 n;\nmov.u32 n, 0;\n"
      "W_LOOP:\nmbarrier.try_wait.parity.shared::cta.b64 p, [%0], %1;\n@p bra W_DONE;\n"
      "add.u32 n, n, 1;\nsetp.lt.u32 p, n, 0x40000;\n@p bra W_LOOP;\ntrap;\nW_DONE:\n}" ::"r"(bar), "r"(parity) : "memory");
}
__device__ __forceinline__ void bulk_load(uint32_t dst, const void* src, uint32_t bytes, uint32_t bar) {
  asm volatile("cp.async.bulk.shared::cluster.global.mbarrier::complete_tx::bytes [%0], [%1], %2, [%3];" ::"r"(dst), "l"(src), "r"(bytes), "r"(bar) : "memory");
}
__device__ __forceinline__ void cp16(uint32_t dst, const void* src) { asm volatile("cp.async.cg.shared.global [%0], [%1], 16;" ::"r"(dst), "l"(src) : "memory"); }
__device__ __forceinline__ void spin_guard(uint32_t t0) { if ((uint32_t)clock() - t0 > (1u << 30)) __trap(); }
__device__ __forceinline__ float tagf(float v, uint32_t tag) { return __uint_as_float((__float_as_uint(v) & ~1u) | tag); }
__device__ __forceinline__ float untag(float v) { return __uint_as_float(__float_as_uint(v) & ~1u); }
__device__ __forceinline__ void st_x2(float2* p, float a, float b) { asm volatile("st.relaxed.gpu.global.v2.f32 [%0], {%1,%2};" ::"l"(p), "f"(a), "f"(b) : "memory"); }
__device__ __forceinline__ float2 ld_x2(const float2* p) { float2 v; asm volatile("ld.relaxed.gpu.global.v2.f32 {%0,%1}, [%2];" : "=f"(v.x), "=f"(v.y) : "l"(p) : "memory"); return v; }
__device__ __forceinline__ void st_u2(uint2* p, uint32_t a, uint32_t b) { asm volatile("st.relaxed.gpu.global.v2.u32 [%0], {%1,%2};" ::"l"(p), "r"(a), "r"(b) : "memory"); }
__device__ __forceinline__ void prefetch2d(const CUtensorMap* m, int c0, int c1) { asm volatile("cp.async.bulk.prefetch.tensor.2d.L2.global [%0, {%1, %2}];" ::"l"(m), "r"(c0), "r"(c1) : "memory"); }
__device__ __forceinline__ void prefetch1d(const void* p, uint32_t bytes) { asm volatile("cp.async.bulk.prefetch.L2.global [%0], %1;" ::"l"(p), "r"(bytes) : "memory"); }
__device__ __forceinline__ uint32_t ld_x1(const void* p) { uint32_t v; asm volatile("ld.relaxed.gpu.global.u32 %0, [%1];" : "=r"(v) : "l"(p) : "memory"); return v; }
__device__ __forceinline__ uint4 ld_x4(const void* p) { uint4 v; asm volatile("ld.relaxed.gpu.global.v4.u32 {%0,%1,%2,%3}, [%4];" : "=r"(v.x), "=r"(v.y), "=r"(v.z), "=r"(v.w) : "l"(p) : "memory"); return v; }
__device__ __forceinline__ void st_x4(void* p, uint32_t a, uint32_t b, uint32_t c, uint32_t d) { asm volatile("st.relaxed.gpu.global.v4.u32 [%0], {%1,%2,%3,%4};" ::"l"(p), "r"(a), "r"(b), "r"(c), "r"(d) : "memory"); }
__device__ __forceinline__ uint32_t mapa(uint32_t a, uint32_t cta) { uint32_t r; asm volatile("mapa.shared::cluster.u32 %0, %1, %2;" : "=r"(r) : "r"(a), "r"(cta)); return r; }
__device__ __forceinline__ void stsm4t(uint32_t a, uint32_t r0, uint32_t r1, uint32_t r2, uint32_t r3) {
  asm volatile("stmatrix.sync.aligned.m8n8.x4.trans.shared.b16 [%0], {%1,%2,%3,%4};" ::"r"(a), "r"(r0), "r"(r1), "r"(r2), "r"(r3) : "memory");
}
__device__ __forceinline__ void hint_add(unsigned* p) { asm volatile("red.relaxed.gpu.global.add.u32 [%0], 1;" ::"l"(p) : "memory"); }
__device__ __forceinline__ void hint_wait(const unsigned* p, unsigned target) {
  const uint32_t t0 = (uint32_t)clock();
  while ((int)(ld_x1(p) - target) < 0) spin_guard(t0);
}
__device__ __forceinline__ void bulk_done_signal(unsigned* p) {
  asm volatile("cp.async.bulk.commit_group;\ncp.async.bulk.wait_group 0;\nfence.proxy.async.global;" ::: "memory");
  hint_add(p);
}
__device__ __forceinline__ void flag_wait(const unsigned* p, unsigned target) {
  hint_wait(p, target);
  asm volatile("fence.proxy.async.global;" ::: "memory");
}
__device__ __forceinline__ void tma2d(uint32_t dst, const CUtensorMap* m, uint32_t bar, int c0, int c1) {
  asm volatile("cp.async.bulk.tensor.2d.shared::cluster.global.mbarrier::complete_tx::bytes [%0], [%1, {%3, %4}], [%2];" ::"r"(dst), "l"(m), "r"(bar), "r"(c0), "r"(c1) : "memory");
}
__device__ __forceinline__ void tma3d(uint32_t dst, const CUtensorMap* m, uint32_t bar, int c0, int c1, int c2) {
  asm volatile("cp.async.bulk.tensor.3d.shared::cluster.global.mbarrier::complete_tx::bytes [%0], [%1, {%3, %4, %5}], [%2];" ::"r"(dst), "l"(m), "r"(bar), "r"(c0), "r"(c1), "r"(c2) : "memory");
}
__device__ __forceinline__ void tma4d(uint32_t dst, const CUtensorMap* m, uint32_t bar, int c0, int c1, int c2, int c3) {
  asm volatile("cp.async.bulk.tensor.4d.shared::cluster.global.mbarrier::complete_tx::bytes [%0], [%1, {%3, %4, %5, %6}], [%2];" ::"r"(dst), "l"(m), "r"(bar), "r"(c0), "r"(c1), "r"(c2), "r"(c3) : "memory");
}
__device__ __forceinline__ void wg_fence() { asm volatile("wgmma.fence.sync.aligned;" ::: "memory"); }
__device__ __forceinline__ void wg_commit() { asm volatile("wgmma.commit_group.sync.aligned;" ::: "memory"); }
template <int N> __device__ __forceinline__ void wg_wait() { asm volatile("wgmma.wait_group.sync.aligned %0;" ::"n"(N) : "memory"); }
template <int O, int N, int NN> __device__ __forceinline__ void fence_regs(float (&d)[NN]) {
#pragma unroll
  for (int i = 0; i < N; i++) asm volatile("" : "+f"(d[O + i])::"memory");
}
__device__ __forceinline__ uint32_t pack_bf16(float lo, float hi) {
  uint32_t r; asm("cvt.rn.bf16x2.f32 %0, %1, %2;" : "=r"(r) : "f"(hi), "f"(lo)); return r;
}
__device__ __forceinline__ uint32_t pack_pin(float lo, float hi) {
  uint32_t r; asm volatile("cvt.rn.bf16x2.f32 %0, %1, %2;" : "=r"(r) : "f"(hi), "f"(lo) : "memory"); return r;
}
__device__ __forceinline__ float bf_lo(uint32_t u) { return __uint_as_float(u << 16); }
__device__ __forceinline__ float bf_hi(uint32_t u) { return __uint_as_float(u & 0xffff0000u); }

__device__ __forceinline__ uint64_t d128(uint32_t lo) { uint64_t d; asm("mov.b64 %0, {%1, 0x40000040};" : "=l"(d) : "r"(lo)); return d; }
__device__ __forceinline__ uint64_t d64(uint32_t lo) { uint64_t d; asm("mov.b64 %0, {%1, 0x80000020};" : "=l"(d) : "r"(lo)); return d; }
template<int O,int TB,int ACC,int NN> __device__ __forceinline__ void mma_ss64(float (&d)[NN], uint64_t da, uint64_t db, int sd = 0){
  if constexpr (ACC == 1) asm volatile("wgmma.mma_async.sync.aligned.m64n64k16.f32.bf16.bf16 {%0,%1,%2,%3,%4,%5,%6,%7,%8,%9,%10,%11,%12,%13,%14,%15,%16,%17,%18,%19,%20,%21,%22,%23,%24,%25,%26,%27,%28,%29,%30,%31}, %32, %33, 1, 1, 1, %35, %34;"
   : "+f"(d[O+0]), "+f"(d[O+1]), "+f"(d[O+2]), "+f"(d[O+3]), "+f"(d[O+4]), "+f"(d[O+5]), "+f"(d[O+6]), "+f"(d[O+7]), "+f"(d[O+8]), "+f"(d[O+9]), "+f"(d[O+10]), "+f"(d[O+11]), "+f"(d[O+12]), "+f"(d[O+13]), "+f"(d[O+14]), "+f"(d[O+15]), "+f"(d[O+16]), "+f"(d[O+17]), "+f"(d[O+18]), "+f"(d[O+19]), "+f"(d[O+20]), "+f"(d[O+21]), "+f"(d[O+22]), "+f"(d[O+23]), "+f"(d[O+24]), "+f"(d[O+25]), "+f"(d[O+26]), "+f"(d[O+27]), "+f"(d[O+28]), "+f"(d[O+29]), "+f"(d[O+30]), "+f"(d[O+31])
   : "l"(da), "l"(db), "n"(TB & 1), "n"(TB >> 1));
  else if constexpr (ACC == 0) asm volatile("wgmma.mma_async.sync.aligned.m64n64k16.f32.bf16.bf16 {%0,%1,%2,%3,%4,%5,%6,%7,%8,%9,%10,%11,%12,%13,%14,%15,%16,%17,%18,%19,%20,%21,%22,%23,%24,%25,%26,%27,%28,%29,%30,%31}, %32, %33, 0, 1, 1, %35, %34;"
   : "=f"(d[O+0]), "=f"(d[O+1]), "=f"(d[O+2]), "=f"(d[O+3]), "=f"(d[O+4]), "=f"(d[O+5]), "=f"(d[O+6]), "=f"(d[O+7]), "=f"(d[O+8]), "=f"(d[O+9]), "=f"(d[O+10]), "=f"(d[O+11]), "=f"(d[O+12]), "=f"(d[O+13]), "=f"(d[O+14]), "=f"(d[O+15]), "=f"(d[O+16]), "=f"(d[O+17]), "=f"(d[O+18]), "=f"(d[O+19]), "=f"(d[O+20]), "=f"(d[O+21]), "=f"(d[O+22]), "=f"(d[O+23]), "=f"(d[O+24]), "=f"(d[O+25]), "=f"(d[O+26]), "=f"(d[O+27]), "=f"(d[O+28]), "=f"(d[O+29]), "=f"(d[O+30]), "=f"(d[O+31])
   : "l"(da), "l"(db), "n"(TB & 1), "n"(TB >> 1));
  else asm volatile("{\n.reg .pred p;\nsetp.ne.b32 p, %36, 0;\nwgmma.mma_async.sync.aligned.m64n64k16.f32.bf16.bf16 {%0,%1,%2,%3,%4,%5,%6,%7,%8,%9,%10,%11,%12,%13,%14,%15,%16,%17,%18,%19,%20,%21,%22,%23,%24,%25,%26,%27,%28,%29,%30,%31}, %32, %33, p, 1, 1, %35, %34;\n}"
   : "+f"(d[O+0]), "+f"(d[O+1]), "+f"(d[O+2]), "+f"(d[O+3]), "+f"(d[O+4]), "+f"(d[O+5]), "+f"(d[O+6]), "+f"(d[O+7]), "+f"(d[O+8]), "+f"(d[O+9]), "+f"(d[O+10]), "+f"(d[O+11]), "+f"(d[O+12]), "+f"(d[O+13]), "+f"(d[O+14]), "+f"(d[O+15]), "+f"(d[O+16]), "+f"(d[O+17]), "+f"(d[O+18]), "+f"(d[O+19]), "+f"(d[O+20]), "+f"(d[O+21]), "+f"(d[O+22]), "+f"(d[O+23]), "+f"(d[O+24]), "+f"(d[O+25]), "+f"(d[O+26]), "+f"(d[O+27]), "+f"(d[O+28]), "+f"(d[O+29]), "+f"(d[O+30]), "+f"(d[O+31])
   : "l"(da), "l"(db), "n"(TB & 1), "n"(TB >> 1), "r"(sd));
}
template<int O,int TB,int ACC,int NN> __device__ __forceinline__ void mma_rs64(float (&d)[NN], uint32_t a0, uint32_t a1, uint32_t a2, uint32_t a3, uint64_t db, int sd = 0){
  if constexpr (ACC == 1) asm volatile("wgmma.mma_async.sync.aligned.m64n64k16.f32.bf16.bf16 {%0,%1,%2,%3,%4,%5,%6,%7,%8,%9,%10,%11,%12,%13,%14,%15,%16,%17,%18,%19,%20,%21,%22,%23,%24,%25,%26,%27,%28,%29,%30,%31}, {%32,%33,%34,%35}, %36, 1, 1, 1, %37;"
   : "+f"(d[O+0]), "+f"(d[O+1]), "+f"(d[O+2]), "+f"(d[O+3]), "+f"(d[O+4]), "+f"(d[O+5]), "+f"(d[O+6]), "+f"(d[O+7]), "+f"(d[O+8]), "+f"(d[O+9]), "+f"(d[O+10]), "+f"(d[O+11]), "+f"(d[O+12]), "+f"(d[O+13]), "+f"(d[O+14]), "+f"(d[O+15]), "+f"(d[O+16]), "+f"(d[O+17]), "+f"(d[O+18]), "+f"(d[O+19]), "+f"(d[O+20]), "+f"(d[O+21]), "+f"(d[O+22]), "+f"(d[O+23]), "+f"(d[O+24]), "+f"(d[O+25]), "+f"(d[O+26]), "+f"(d[O+27]), "+f"(d[O+28]), "+f"(d[O+29]), "+f"(d[O+30]), "+f"(d[O+31])
   : "r"(a0), "r"(a1), "r"(a2), "r"(a3), "l"(db), "n"(TB));
  else if constexpr (ACC == 0) asm volatile("wgmma.mma_async.sync.aligned.m64n64k16.f32.bf16.bf16 {%0,%1,%2,%3,%4,%5,%6,%7,%8,%9,%10,%11,%12,%13,%14,%15,%16,%17,%18,%19,%20,%21,%22,%23,%24,%25,%26,%27,%28,%29,%30,%31}, {%32,%33,%34,%35}, %36, 0, 1, 1, %37;"
   : "=f"(d[O+0]), "=f"(d[O+1]), "=f"(d[O+2]), "=f"(d[O+3]), "=f"(d[O+4]), "=f"(d[O+5]), "=f"(d[O+6]), "=f"(d[O+7]), "=f"(d[O+8]), "=f"(d[O+9]), "=f"(d[O+10]), "=f"(d[O+11]), "=f"(d[O+12]), "=f"(d[O+13]), "=f"(d[O+14]), "=f"(d[O+15]), "=f"(d[O+16]), "=f"(d[O+17]), "=f"(d[O+18]), "=f"(d[O+19]), "=f"(d[O+20]), "=f"(d[O+21]), "=f"(d[O+22]), "=f"(d[O+23]), "=f"(d[O+24]), "=f"(d[O+25]), "=f"(d[O+26]), "=f"(d[O+27]), "=f"(d[O+28]), "=f"(d[O+29]), "=f"(d[O+30]), "=f"(d[O+31])
   : "r"(a0), "r"(a1), "r"(a2), "r"(a3), "l"(db), "n"(TB));
  else asm volatile("{\n.reg .pred p;\nsetp.ne.b32 p, %38, 0;\nwgmma.mma_async.sync.aligned.m64n64k16.f32.bf16.bf16 {%0,%1,%2,%3,%4,%5,%6,%7,%8,%9,%10,%11,%12,%13,%14,%15,%16,%17,%18,%19,%20,%21,%22,%23,%24,%25,%26,%27,%28,%29,%30,%31}, {%32,%33,%34,%35}, %36, p, 1, 1, %37;\n}"
   : "+f"(d[O+0]), "+f"(d[O+1]), "+f"(d[O+2]), "+f"(d[O+3]), "+f"(d[O+4]), "+f"(d[O+5]), "+f"(d[O+6]), "+f"(d[O+7]), "+f"(d[O+8]), "+f"(d[O+9]), "+f"(d[O+10]), "+f"(d[O+11]), "+f"(d[O+12]), "+f"(d[O+13]), "+f"(d[O+14]), "+f"(d[O+15]), "+f"(d[O+16]), "+f"(d[O+17]), "+f"(d[O+18]), "+f"(d[O+19]), "+f"(d[O+20]), "+f"(d[O+21]), "+f"(d[O+22]), "+f"(d[O+23]), "+f"(d[O+24]), "+f"(d[O+25]), "+f"(d[O+26]), "+f"(d[O+27]), "+f"(d[O+28]), "+f"(d[O+29]), "+f"(d[O+30]), "+f"(d[O+31])
   : "r"(a0), "r"(a1), "r"(a2), "r"(a3), "l"(db), "n"(TB), "r"(sd));
}
template<int O,int TB,int ACC,int NN> __device__ __forceinline__ void mma_ss128(float (&d)[NN], uint64_t da, uint64_t db, int sd = 0){
  if constexpr (ACC == 1) asm volatile("wgmma.mma_async.sync.aligned.m64n128k16.f32.bf16.bf16 {%0,%1,%2,%3,%4,%5,%6,%7,%8,%9,%10,%11,%12,%13,%14,%15,%16,%17,%18,%19,%20,%21,%22,%23,%24,%25,%26,%27,%28,%29,%30,%31,%32,%33,%34,%35,%36,%37,%38,%39,%40,%41,%42,%43,%44,%45,%46,%47,%48,%49,%50,%51,%52,%53,%54,%55,%56,%57,%58,%59,%60,%61,%62,%63}, %64, %65, 1, 1, 1, %67, %66;"
   : "+f"(d[O+0]), "+f"(d[O+1]), "+f"(d[O+2]), "+f"(d[O+3]), "+f"(d[O+4]), "+f"(d[O+5]), "+f"(d[O+6]), "+f"(d[O+7]), "+f"(d[O+8]), "+f"(d[O+9]), "+f"(d[O+10]), "+f"(d[O+11]), "+f"(d[O+12]), "+f"(d[O+13]), "+f"(d[O+14]), "+f"(d[O+15]), "+f"(d[O+16]), "+f"(d[O+17]), "+f"(d[O+18]), "+f"(d[O+19]), "+f"(d[O+20]), "+f"(d[O+21]), "+f"(d[O+22]), "+f"(d[O+23]), "+f"(d[O+24]), "+f"(d[O+25]), "+f"(d[O+26]), "+f"(d[O+27]), "+f"(d[O+28]), "+f"(d[O+29]), "+f"(d[O+30]), "+f"(d[O+31]), "+f"(d[O+32]), "+f"(d[O+33]), "+f"(d[O+34]), "+f"(d[O+35]), "+f"(d[O+36]), "+f"(d[O+37]), "+f"(d[O+38]), "+f"(d[O+39]), "+f"(d[O+40]), "+f"(d[O+41]), "+f"(d[O+42]), "+f"(d[O+43]), "+f"(d[O+44]), "+f"(d[O+45]), "+f"(d[O+46]), "+f"(d[O+47]), "+f"(d[O+48]), "+f"(d[O+49]), "+f"(d[O+50]), "+f"(d[O+51]), "+f"(d[O+52]), "+f"(d[O+53]), "+f"(d[O+54]), "+f"(d[O+55]), "+f"(d[O+56]), "+f"(d[O+57]), "+f"(d[O+58]), "+f"(d[O+59]), "+f"(d[O+60]), "+f"(d[O+61]), "+f"(d[O+62]), "+f"(d[O+63])
   : "l"(da), "l"(db), "n"(TB & 1), "n"(TB >> 1));
  else if constexpr (ACC == 0) asm volatile("wgmma.mma_async.sync.aligned.m64n128k16.f32.bf16.bf16 {%0,%1,%2,%3,%4,%5,%6,%7,%8,%9,%10,%11,%12,%13,%14,%15,%16,%17,%18,%19,%20,%21,%22,%23,%24,%25,%26,%27,%28,%29,%30,%31,%32,%33,%34,%35,%36,%37,%38,%39,%40,%41,%42,%43,%44,%45,%46,%47,%48,%49,%50,%51,%52,%53,%54,%55,%56,%57,%58,%59,%60,%61,%62,%63}, %64, %65, 0, 1, 1, %67, %66;"
   : "=f"(d[O+0]), "=f"(d[O+1]), "=f"(d[O+2]), "=f"(d[O+3]), "=f"(d[O+4]), "=f"(d[O+5]), "=f"(d[O+6]), "=f"(d[O+7]), "=f"(d[O+8]), "=f"(d[O+9]), "=f"(d[O+10]), "=f"(d[O+11]), "=f"(d[O+12]), "=f"(d[O+13]), "=f"(d[O+14]), "=f"(d[O+15]), "=f"(d[O+16]), "=f"(d[O+17]), "=f"(d[O+18]), "=f"(d[O+19]), "=f"(d[O+20]), "=f"(d[O+21]), "=f"(d[O+22]), "=f"(d[O+23]), "=f"(d[O+24]), "=f"(d[O+25]), "=f"(d[O+26]), "=f"(d[O+27]), "=f"(d[O+28]), "=f"(d[O+29]), "=f"(d[O+30]), "=f"(d[O+31]), "=f"(d[O+32]), "=f"(d[O+33]), "=f"(d[O+34]), "=f"(d[O+35]), "=f"(d[O+36]), "=f"(d[O+37]), "=f"(d[O+38]), "=f"(d[O+39]), "=f"(d[O+40]), "=f"(d[O+41]), "=f"(d[O+42]), "=f"(d[O+43]), "=f"(d[O+44]), "=f"(d[O+45]), "=f"(d[O+46]), "=f"(d[O+47]), "=f"(d[O+48]), "=f"(d[O+49]), "=f"(d[O+50]), "=f"(d[O+51]), "=f"(d[O+52]), "=f"(d[O+53]), "=f"(d[O+54]), "=f"(d[O+55]), "=f"(d[O+56]), "=f"(d[O+57]), "=f"(d[O+58]), "=f"(d[O+59]), "=f"(d[O+60]), "=f"(d[O+61]), "=f"(d[O+62]), "=f"(d[O+63])
   : "l"(da), "l"(db), "n"(TB & 1), "n"(TB >> 1));
  else asm volatile("{\n.reg .pred p;\nsetp.ne.b32 p, %68, 0;\nwgmma.mma_async.sync.aligned.m64n128k16.f32.bf16.bf16 {%0,%1,%2,%3,%4,%5,%6,%7,%8,%9,%10,%11,%12,%13,%14,%15,%16,%17,%18,%19,%20,%21,%22,%23,%24,%25,%26,%27,%28,%29,%30,%31,%32,%33,%34,%35,%36,%37,%38,%39,%40,%41,%42,%43,%44,%45,%46,%47,%48,%49,%50,%51,%52,%53,%54,%55,%56,%57,%58,%59,%60,%61,%62,%63}, %64, %65, p, 1, 1, %67, %66;\n}"
   : "+f"(d[O+0]), "+f"(d[O+1]), "+f"(d[O+2]), "+f"(d[O+3]), "+f"(d[O+4]), "+f"(d[O+5]), "+f"(d[O+6]), "+f"(d[O+7]), "+f"(d[O+8]), "+f"(d[O+9]), "+f"(d[O+10]), "+f"(d[O+11]), "+f"(d[O+12]), "+f"(d[O+13]), "+f"(d[O+14]), "+f"(d[O+15]), "+f"(d[O+16]), "+f"(d[O+17]), "+f"(d[O+18]), "+f"(d[O+19]), "+f"(d[O+20]), "+f"(d[O+21]), "+f"(d[O+22]), "+f"(d[O+23]), "+f"(d[O+24]), "+f"(d[O+25]), "+f"(d[O+26]), "+f"(d[O+27]), "+f"(d[O+28]), "+f"(d[O+29]), "+f"(d[O+30]), "+f"(d[O+31]), "+f"(d[O+32]), "+f"(d[O+33]), "+f"(d[O+34]), "+f"(d[O+35]), "+f"(d[O+36]), "+f"(d[O+37]), "+f"(d[O+38]), "+f"(d[O+39]), "+f"(d[O+40]), "+f"(d[O+41]), "+f"(d[O+42]), "+f"(d[O+43]), "+f"(d[O+44]), "+f"(d[O+45]), "+f"(d[O+46]), "+f"(d[O+47]), "+f"(d[O+48]), "+f"(d[O+49]), "+f"(d[O+50]), "+f"(d[O+51]), "+f"(d[O+52]), "+f"(d[O+53]), "+f"(d[O+54]), "+f"(d[O+55]), "+f"(d[O+56]), "+f"(d[O+57]), "+f"(d[O+58]), "+f"(d[O+59]), "+f"(d[O+60]), "+f"(d[O+61]), "+f"(d[O+62]), "+f"(d[O+63])
   : "l"(da), "l"(db), "n"(TB & 1), "n"(TB >> 1), "r"(sd));
}
template<int O,int TB,int ACC,int NN> __device__ __forceinline__ void mma_rs128(float (&d)[NN], uint32_t a0, uint32_t a1, uint32_t a2, uint32_t a3, uint64_t db, int sd = 0){
  if constexpr (ACC == 1) asm volatile("wgmma.mma_async.sync.aligned.m64n128k16.f32.bf16.bf16 {%0,%1,%2,%3,%4,%5,%6,%7,%8,%9,%10,%11,%12,%13,%14,%15,%16,%17,%18,%19,%20,%21,%22,%23,%24,%25,%26,%27,%28,%29,%30,%31,%32,%33,%34,%35,%36,%37,%38,%39,%40,%41,%42,%43,%44,%45,%46,%47,%48,%49,%50,%51,%52,%53,%54,%55,%56,%57,%58,%59,%60,%61,%62,%63}, {%64,%65,%66,%67}, %68, 1, 1, 1, %69;"
   : "+f"(d[O+0]), "+f"(d[O+1]), "+f"(d[O+2]), "+f"(d[O+3]), "+f"(d[O+4]), "+f"(d[O+5]), "+f"(d[O+6]), "+f"(d[O+7]), "+f"(d[O+8]), "+f"(d[O+9]), "+f"(d[O+10]), "+f"(d[O+11]), "+f"(d[O+12]), "+f"(d[O+13]), "+f"(d[O+14]), "+f"(d[O+15]), "+f"(d[O+16]), "+f"(d[O+17]), "+f"(d[O+18]), "+f"(d[O+19]), "+f"(d[O+20]), "+f"(d[O+21]), "+f"(d[O+22]), "+f"(d[O+23]), "+f"(d[O+24]), "+f"(d[O+25]), "+f"(d[O+26]), "+f"(d[O+27]), "+f"(d[O+28]), "+f"(d[O+29]), "+f"(d[O+30]), "+f"(d[O+31]), "+f"(d[O+32]), "+f"(d[O+33]), "+f"(d[O+34]), "+f"(d[O+35]), "+f"(d[O+36]), "+f"(d[O+37]), "+f"(d[O+38]), "+f"(d[O+39]), "+f"(d[O+40]), "+f"(d[O+41]), "+f"(d[O+42]), "+f"(d[O+43]), "+f"(d[O+44]), "+f"(d[O+45]), "+f"(d[O+46]), "+f"(d[O+47]), "+f"(d[O+48]), "+f"(d[O+49]), "+f"(d[O+50]), "+f"(d[O+51]), "+f"(d[O+52]), "+f"(d[O+53]), "+f"(d[O+54]), "+f"(d[O+55]), "+f"(d[O+56]), "+f"(d[O+57]), "+f"(d[O+58]), "+f"(d[O+59]), "+f"(d[O+60]), "+f"(d[O+61]), "+f"(d[O+62]), "+f"(d[O+63])
   : "r"(a0), "r"(a1), "r"(a2), "r"(a3), "l"(db), "n"(TB));
  else if constexpr (ACC == 0) asm volatile("wgmma.mma_async.sync.aligned.m64n128k16.f32.bf16.bf16 {%0,%1,%2,%3,%4,%5,%6,%7,%8,%9,%10,%11,%12,%13,%14,%15,%16,%17,%18,%19,%20,%21,%22,%23,%24,%25,%26,%27,%28,%29,%30,%31,%32,%33,%34,%35,%36,%37,%38,%39,%40,%41,%42,%43,%44,%45,%46,%47,%48,%49,%50,%51,%52,%53,%54,%55,%56,%57,%58,%59,%60,%61,%62,%63}, {%64,%65,%66,%67}, %68, 0, 1, 1, %69;"
   : "=f"(d[O+0]), "=f"(d[O+1]), "=f"(d[O+2]), "=f"(d[O+3]), "=f"(d[O+4]), "=f"(d[O+5]), "=f"(d[O+6]), "=f"(d[O+7]), "=f"(d[O+8]), "=f"(d[O+9]), "=f"(d[O+10]), "=f"(d[O+11]), "=f"(d[O+12]), "=f"(d[O+13]), "=f"(d[O+14]), "=f"(d[O+15]), "=f"(d[O+16]), "=f"(d[O+17]), "=f"(d[O+18]), "=f"(d[O+19]), "=f"(d[O+20]), "=f"(d[O+21]), "=f"(d[O+22]), "=f"(d[O+23]), "=f"(d[O+24]), "=f"(d[O+25]), "=f"(d[O+26]), "=f"(d[O+27]), "=f"(d[O+28]), "=f"(d[O+29]), "=f"(d[O+30]), "=f"(d[O+31]), "=f"(d[O+32]), "=f"(d[O+33]), "=f"(d[O+34]), "=f"(d[O+35]), "=f"(d[O+36]), "=f"(d[O+37]), "=f"(d[O+38]), "=f"(d[O+39]), "=f"(d[O+40]), "=f"(d[O+41]), "=f"(d[O+42]), "=f"(d[O+43]), "=f"(d[O+44]), "=f"(d[O+45]), "=f"(d[O+46]), "=f"(d[O+47]), "=f"(d[O+48]), "=f"(d[O+49]), "=f"(d[O+50]), "=f"(d[O+51]), "=f"(d[O+52]), "=f"(d[O+53]), "=f"(d[O+54]), "=f"(d[O+55]), "=f"(d[O+56]), "=f"(d[O+57]), "=f"(d[O+58]), "=f"(d[O+59]), "=f"(d[O+60]), "=f"(d[O+61]), "=f"(d[O+62]), "=f"(d[O+63])
   : "r"(a0), "r"(a1), "r"(a2), "r"(a3), "l"(db), "n"(TB));
  else asm volatile("{\n.reg .pred p;\nsetp.ne.b32 p, %70, 0;\nwgmma.mma_async.sync.aligned.m64n128k16.f32.bf16.bf16 {%0,%1,%2,%3,%4,%5,%6,%7,%8,%9,%10,%11,%12,%13,%14,%15,%16,%17,%18,%19,%20,%21,%22,%23,%24,%25,%26,%27,%28,%29,%30,%31,%32,%33,%34,%35,%36,%37,%38,%39,%40,%41,%42,%43,%44,%45,%46,%47,%48,%49,%50,%51,%52,%53,%54,%55,%56,%57,%58,%59,%60,%61,%62,%63}, {%64,%65,%66,%67}, %68, p, 1, 1, %69;\n}"
   : "+f"(d[O+0]), "+f"(d[O+1]), "+f"(d[O+2]), "+f"(d[O+3]), "+f"(d[O+4]), "+f"(d[O+5]), "+f"(d[O+6]), "+f"(d[O+7]), "+f"(d[O+8]), "+f"(d[O+9]), "+f"(d[O+10]), "+f"(d[O+11]), "+f"(d[O+12]), "+f"(d[O+13]), "+f"(d[O+14]), "+f"(d[O+15]), "+f"(d[O+16]), "+f"(d[O+17]), "+f"(d[O+18]), "+f"(d[O+19]), "+f"(d[O+20]), "+f"(d[O+21]), "+f"(d[O+22]), "+f"(d[O+23]), "+f"(d[O+24]), "+f"(d[O+25]), "+f"(d[O+26]), "+f"(d[O+27]), "+f"(d[O+28]), "+f"(d[O+29]), "+f"(d[O+30]), "+f"(d[O+31]), "+f"(d[O+32]), "+f"(d[O+33]), "+f"(d[O+34]), "+f"(d[O+35]), "+f"(d[O+36]), "+f"(d[O+37]), "+f"(d[O+38]), "+f"(d[O+39]), "+f"(d[O+40]), "+f"(d[O+41]), "+f"(d[O+42]), "+f"(d[O+43]), "+f"(d[O+44]), "+f"(d[O+45]), "+f"(d[O+46]), "+f"(d[O+47]), "+f"(d[O+48]), "+f"(d[O+49]), "+f"(d[O+50]), "+f"(d[O+51]), "+f"(d[O+52]), "+f"(d[O+53]), "+f"(d[O+54]), "+f"(d[O+55]), "+f"(d[O+56]), "+f"(d[O+57]), "+f"(d[O+58]), "+f"(d[O+59]), "+f"(d[O+60]), "+f"(d[O+61]), "+f"(d[O+62]), "+f"(d[O+63])
   : "r"(a0), "r"(a1), "r"(a2), "r"(a3), "l"(db), "n"(TB), "r"(sd));
}

#define NEARLY 0
#define XAHEAD 3
#define WAFTER 7
#define WPACE 100
#define GATE_AT 0
#define TPACE 40
#define PFMODE 0
#define MAPMODE 0
template <int V> struct IC { static constexpr int value = V; };
struct Maps { CUtensorMap x, ft, g32, u32, wr, wi, g64, u64, e, xs, ts, t, d192, d32; };

constexpr int NCTA = 130;
constexpr int U = 16384;
constexpr int TB = 36864;
constexpr int NR = 4;
constexpr int OFF_RING = 8 * U, OFF_Z = 9 * U, OFF_XB = 12 * U, OFF_T = 13 * U, OFF_D = OFF_T, OFF_SP = OFF_T + 12288;
constexpr int OFF_BAR = 14 * U;
constexpr int SMEM_BYTES = OFF_BAR + 512;
constexpr int B_FX = 0, B_FA = 8, B_FT = 12, B_Z = 16, B_W = 20, B_HX = 21, B_TL = 22, B_HP = 23, B_WR = 26;
constexpr int B_EA = 30, B_ET = 34, B_RDY = 38;
constexpr int B_T = 39, B_XS = 40, NBAR = 41;
__host__ __device__ constexpr int rslot(int n) { return n & 3; }
__host__ __device__ constexpr int rpar(int n) { return (n >> 2) & 1; }

__global__ void __cluster_dims__(2, 1, 1) __launch_bounds__(512, 1)
fused_kernel(const __grid_constant__ Maps maps, const __nv_bfloat16* __restrict__ x, const __nv_bfloat16* __restrict__ w_r,
             const __nv_bfloat16* __restrict__ w_i, const __nv_bfloat16* __restrict__ gate_w, __nv_bfloat16* __restrict__ out) {
  extern __shared__ __align__(1024) uint8_t smem[];
  const uint32_t sb = smem_u32(smem);
  const uint32_t bars = sb + OFF_BAR;
  const int tid = threadIdx.x, lane = tid & 31;
  const int warp = __shfl_sync(0xffffffffu, tid >> 5, 0);
  const bool helper = blockIdx.x >= 128;
  const int cl = (blockIdx.x >> 1) & 63, rank = blockIdx.x & 1;
  const int q4 = cl & 3, rb = cl >> 2;
  const int j = 2 * q4 + rank;
  const int f_full = 448 * q4 + (rank ? 256 : 0);
  const int f_half = 448 * q4 + (rank ? 224 : 192);
  const int kg = 2 * j + (rb >> 3), tn = rb & 7;

  if (tid == 64) { PROF_EV(0); PROF_CK(40); }
  auto ring_part = [&](int p, int n, int slot) {
    const uint32_t fb = bars + 8 * (B_FA + slot), dst = sb + OFF_RING + slot * U;
    const bool table = n == 9 || n == 10 || n >= 34;
    const int q = n == 8 ? 0 : n - 10;
    if (p == 0) {
      mbar_expect_tx(fb, U);
      if (n < 8) tma2d(dst, &maps.ft, fb, 64 * n, 64 * j);
      else if (table) tma4d(dst, &maps.e, fb, 0, 0, 0, 2 * rb + (n >= 34 ? n - 34 : n - 9));
      else tma2d(dst, &maps.g64, fb, f_full + 64 * (q >> 3), 64 * (q & 7));
    } else if (p == 1) {
      if (n < 8) { tma2d(dst + 8192, &maps.g32, fb, f_half, 64 * n); tma2d(dst + 12288, &maps.u32, fb, f_half, 64 * n); }
      else if (!table) tma2d(dst + 8192, &maps.u64, fb, f_full + 64 * (q >> 3), 64 * (q & 7));
    }
  };
  auto x_load = [&](int q) {
    mbar_expect_tx(bars + 8 * (B_FX + q), U);
    tma3d(sb + q * U, &maps.x, bars + 8 * (B_FX + q), 64 * q, 0, 2 * rb);
  };
  if (warp < 8) {
    asm volatile("barrier.cluster.arrive.relaxed.aligned;" ::: "memory");
    asm volatile("setmaxnreg.inc.sync.aligned.u32 192;");
    if (tid == 0) PROF_EV(33);
    if (!helper) {
      const int wg = warp >> 2, w = warp & 3, g = lane >> 2, q = lane & 3;
      const bool elect = (tid & 127) == 0;
      const uint32_t ep = ld_x1(&g_epoch[blockIdx.x * 8]);
      float c1[64], cA[64], c2[64], ci[64], ct[64];
      const int zero = blockIdx.x >> 16;
      uint32_t h[56], yf[16];
      const uint32_t d0 = (sb & 0x3FFFF) >> 4;
      const uint32_t dK = d0 | (1u << 16), dN = d0 | (512u << 16), dM = d0 | (256u << 16);
      const uint32_t dX = dK + wg * 512;
      constexpr uint32_t RING = OFF_RING >> 4;
      auto waitA = [&](int n) { mbar_wait(bars + 8 * (B_FA + rslot(n)), rpar(n)); };
      auto freeA = [&](int n) { if (elect) mbar_arrive(bars + 8 * (B_EA + rslot(n))); };
      auto nop = [](int) {};

      asm volatile("bar.sync 0, 384;" ::: "memory");
#pragma unroll 1
      for (int kb = 0; kb < 8; kb++) {
        mbar_wait(bars + 8 * (B_FX + kb), 0); waitA(kb);
        wg_fence();
        const uint64_t dx = d128(dX + kb * 1024), df = d128(dK + RING + rslot(kb) * 1024), dm = d64(dM + RING + 512 + rslot(kb) * 1024);
        mma_ss64<0, 0, 2>(c1, df, dx, kb); mma_ss64<32, 1, 2>(c1, dx, dm, kb);
        wg_commit(); wg_wait<1>();
        if (kb) freeA(kb - 1);
#pragma unroll
        for (int k = 1; k < 4; k++) {
          mma_ss64<0, 0, 1>(c1, df + k * 2, dx + k * 2);
          mma_ss64<32, 1, 1>(c1, dx + k * 2, dm + k * 64);
        }
        wg_commit();
        if (kb == 0 && tid == 0) PROF_EV(1);
      }
      auto ffn_step = [&](auto first, float (&acc)[64], int n, int kb, auto done, auto work) {
        waitA(n);
        wg_fence();
        const uint64_t dx = d128(dX + kb * 1024), db = d128(dN + RING + rslot(n) * 1024);
        mma_ss128<0, 1, decltype(first)::value>(acc, dx, db, zero);
        wg_commit();
        wg_wait<1>();
        done();
#pragma unroll
        for (int k = 1; k < 4; k++) { mma_ss128<0, 1, 1>(acc, dx + k * 2, db + k * 128); work(k - 1); }
        wg_commit();
        work(3);
      };
      const uint32_t tag = (ep + 1) & 1;
      float hm[16];
      ffn_step(IC<0>(), c2, 8, 0, [&] { freeA(7); fence_regs<0, 64>(c1); }, [&](int i) {
#pragma unroll
        for (int e = 4 * i; e < 4 * i + 4; e++) { yf[e] = pack_pin(c1[2 * e], c1[2 * e + 1]); hm[e] = fmaxf(c1[32 + e], 0.f) * c1[48 + e]; }
      });
      fence_regs<0, 16>(hm);
      if (tid == 0) PROF_EV(2);
      {
        waitA(9); waitA(10);
        const uint64_t de = d128(dN + RING + (wg ? rslot(10) : rslot(9)) * 1024);
        wg_fence();
        mma_rs128<0, 1, 0>(cA, yf[0], yf[1], yf[2], yf[3], de);
        wg_commit();
        wg_wait<1>();
        freeA(8);
#pragma unroll
        for (int k = 1; k < 4; k++) mma_rs128<0, 1, 1>(cA, yf[4 * k], yf[4 * k + 1], yf[4 * k + 2], yf[4 * k + 3], de + k * 128);
        wg_commit();
      }
      {
        const int s0 = 2 * rb + wg, kr = 2 * ((s0 & 1) | ((s0 & 4) >> 1));
        const int m = lane >> 3, r = lane & 7;
        const uint32_t a0 = sb + OFF_XB + wg * 8192 + (((w >> 1) * 8 + (m >> 1)) * 2 + (w & 1)) * 256 + (m & 1) * 128 + ((r ^ (kr + (m & 1))) << 4);
        ffn_step(IC<1>(), c2, 11, 1, [&] { freeA(9); freeA(10); fence_regs<0, 64>(cA); }, [&](int i) {
          stsm4t(a0 + i * 1024, pack_bf16(cA[8 * i] - cA[34 + 8 * i], cA[8 * i + 1] - cA[35 + 8 * i]),
                 pack_bf16(cA[32 + 8 * i] + cA[8 * i + 2], cA[33 + 8 * i] + cA[8 * i + 3]),
                 pack_bf16(cA[8 * i + 4] - cA[38 + 8 * i], cA[8 * i + 5] - cA[39 + 8 * i]),
                 pack_bf16(cA[36 + 8 * i] + cA[8 * i + 6], cA[37 + 8 * i] + cA[8 * i + 7]));
        });
        if (j == 0 && w == 0 && g == 0) {
#pragma unroll
          for (int n = 0; n < 8; n++)
#pragma unroll
            for (int ce = 0; ce < 4; ce++)
              *(uint32_t*)(smem + OFF_SP + wg * 512 + ce * 128 + ((n ^ (kr + (ce & 1))) << 4) + 4 * q) =
                  pack_bf16(cA[(ce & 1) * 32 + 4 * n + (ce & 2)], cA[(ce & 1) * 32 + 4 * n + (ce & 2) + 1]);
        }
        asm volatile("fence.proxy.async.shared::cta;" ::: "memory");
        __syncwarp();
        if (lane == 0) mbar_arrive(bars + 8 * B_XS);
        if (tid == 0) PROF_EV(3);
      }
      const float* gp = g_gate + rb * 128 + wg * 64 + w * 16 + g;
      uint32_t gb0 = ld_x1(gp), gb1 = ld_x1(gp + 8);
#pragma unroll 1
      for (int kb = 2; kb < 7; kb++) ffn_step(IC<1>(), c2, 10 + kb, kb, [&] { freeA(9 + kb); }, nop);
      {
        const uint32_t t0 = (uint32_t)clock();
        while (__any_sync(0xffffffffu, ((gb0 ^ tag) | (gb1 ^ tag)) & 1)) { gb0 = ld_x1(gp); gb1 = ld_x1(gp + 8); spin_guard(t0); }
      }
      const float g0 = __uint_as_float(gb0 & ~1u), g1 = __uint_as_float(gb1 & ~1u);
      const float o0 = 1.0f - g0, o1 = 1.0f - g1;
      uint32_t hp[8];
      ffn_step(IC<1>(), c2, 17, 7, [&] { freeA(16); }, [&](int i) {
        hp[2 * i] = pack_pin(hm[4 * i] * o0, hm[4 * i + 1] * o0); hp[2 * i + 1] = pack_pin(hm[4 * i + 2] * o1, hm[4 * i + 3] * o1);
      });
      auto glu = [&](float (&acc)[64], int ho, int i0, int i1) {
#pragma unroll
        for (int i = i0; i < i1; i++) {
          const float o = (i & 1) ? o1 : o0;
          h[ho + i] = pack_pin(fmaxf(acc[2 * i], 0.f) * acc[32 + 2 * i] * o, fmaxf(acc[2 * i + 1], 0.f) * acc[33 + 2 * i] * o);
        }
      };
      ffn_step(IC<2>(), cA, 18, 0, [&] { freeA(17); fence_regs<0, 64>(c2); }, [&](int i) { glu(c2, 0, 2 * i, 2 * i + 2); });
      if (tid == 0) PROF_EV(4);
      ffn_step(IC<1>(), cA, 19, 1, [&] { freeA(18); }, [&](int i) { glu(c2, 0, 8 + 2 * i, 10 + 2 * i); });
#pragma unroll 1
      for (int kb = 2; kb < 8; kb++) ffn_step(IC<1>(), cA, 18 + kb, kb, [&] { freeA(17 + kb); }, nop);
      ffn_step(IC<2>(), c2, 26, 0, [&] { freeA(25); fence_regs<0, 64>(cA); }, [&](int i) { glu(cA, 16, 2 * i, 2 * i + 2); });
      if (tid == 0) PROF_EV(5);
      ffn_step(IC<1>(), c2, 27, 1, [&] { freeA(26); }, [&](int i) { glu(cA, 16, 8 + 2 * i, 10 + 2 * i); });
#pragma unroll 1
      for (int kb = 2; kb < 8; kb++)
        ffn_step(IC<1>(), c2, 26 + kb, kb, [&] {
          freeA(25 + kb);
          if (kb >= 3 && (kb & 1) && elect) mbar_arrive(bars + 8 * (B_ET + ((kb - 3) >> 1)));
        }, nop);
      wg_wait<0>();
      if (elect) mbar_arrive(bars + 8 * (B_ET + 3));
      fence_regs<0, 64>(c2);
      glu(c2, 32, 0, 16);
#pragma unroll
      for (int i = 0; i < 8; i++) h[48 + i] = hp[i] ^ zero;
      if (wg) waitA(35); else waitA(34);
      if (tid == 0) PROF_EV(6);
      mbar_wait(bars + 8 * (j == 0 ? B_T : B_TL), 0);
      if (tid == 0) PROF_EV(7);
      wg_fence();
      {
        const uint64_t dt = d128(dN + (OFF_T >> 4) + wg * 512), de = d128(dK + RING + (wg ? rslot(35) : rslot(34)) * 1024);
        mma_ss64<0, 1, 0>(ci, de, dt);
        mma_ss64<32, 1, 0>(ci, de + 512, dt);
#pragma unroll
        for (int k = 1; k < 4; k++) {
          mma_ss64<0, 1, 1>(ci, de + k * 2, dt + k * 128);
          mma_ss64<32, 1, 1>(ci, de + (512 + k * 2), dt + k * 128);
        }
      }
      wg_commit();

      auto head = [&](auto off, int t) {
        constexpr int O = decltype(off)::value;
        mbar_wait(bars + 8 * (B_FT + (t & 3)), t >> 2);
        const uint64_t db = d128(dN + (t & 3) * (TB >> 4));
        wg_fence();
        mma_rs64<O, 1, 0>(ct, h[0], h[1], h[2], h[3], db);
#pragma unroll
        for (int k = 1; k < 6; k++) mma_rs64<O, 1, 1>(ct, h[4 * k], h[4 * k + 1], h[4 * k + 2], h[4 * k + 3], db + k * 128);
        wg_commit();
        wg_wait<1>();
      };
      auto rest = [&](auto off, int t) {
        constexpr int O = decltype(off)::value;
        const uint64_t db = d128(dN + (t & 3) * (TB >> 4));
        wg_fence();
#pragma unroll
        for (int k = 6; k < 14; k++) mma_rs64<O, 1, 1>(ct, h[4 * k], h[4 * k + 1], h[4 * k + 2], h[4 * k + 3], db + k * 128);
#pragma unroll
        for (int k = 0; k < 4; k++) mma_rs64<O, 1, 1>(ct, yf[4 * k], yf[4 * k + 1], yf[4 * k + 2], yf[4 * k + 3], db + (14 + k) * 128);
        wg_commit();
      };
      auto freeT = [&](int t) { if (elect) mbar_arrive(bars + 8 * (B_ET + t)); };
      const uint32_t peerZ = mapa(sb + OFF_Z + tid * 16, rank ^ 1), peerB = mapa(bars + 8 * B_Z, rank ^ 1);
      auto send_peer = [&](auto off, int z) {
        constexpr int O = decltype(off)::value;
        fence_regs<O, 32>(ct);
#pragma unroll
        for (int i = 0; i < 4; i++)
          asm volatile("st.async.weak.shared::cluster.mbarrier::complete_tx::bytes.v4.b32 [%0], {%1,%2,%3,%4}, [%5];" ::"r"(peerZ + z * U + i * 4096),
                       "r"(pack_bf16(ct[O + 8 * i], ct[O + 8 * i + 1])), "r"(pack_bf16(ct[O + 8 * i + 2], ct[O + 8 * i + 3])),
                       "r"(pack_bf16(ct[O + 8 * i + 4], ct[O + 8 * i + 5])), "r"(pack_bf16(ct[O + 8 * i + 6], ct[O + 8 * i + 7])), "r"(peerB + 8 * z) : "memory");
      };
      auto send_grid = [&](auto off, int z) {
        constexpr int O = decltype(off)::value;
        fence_regs<O, 32>(ct);
        mbar_wait(bars + 8 * (B_Z + z), 0);
        uint4* dst = g_part + (size_t)((rb * 8 + 2 * ((q4 + z + 1) & 3) + rank) * 3 + z) * 1024 + tid;
#pragma unroll
        for (int i = 0; i < 4; i++) {
          const uint4 p = *(const uint4*)(smem + OFF_Z + z * U + i * 4096 + tid * 16);
          st_x4(dst + i * 256, (pack_bf16(ct[O + 8 * i] + bf_lo(p.x), ct[O + 8 * i + 1] + bf_hi(p.x)) & ~1u) | tag,
                pack_bf16(ct[O + 8 * i + 2] + bf_lo(p.y), ct[O + 8 * i + 3] + bf_hi(p.y)),
                pack_bf16(ct[O + 8 * i + 4] + bf_lo(p.z), ct[O + 8 * i + 5] + bf_hi(p.z)),
                pack_bf16(ct[O + 8 * i + 6] + bf_lo(p.w), ct[O + 8 * i + 7] + bf_hi(p.w)));
        }
        __syncwarp();
        if (lane == 0) hint_add(&g_cntP[32 * (rb * 8 + 2 * ((q4 + z + 1) & 3) + rank) + z]);
      };
      asm volatile("barrier.cluster.wait.aligned;" ::: "memory");
      head(IC<0>(), 0);
      if (elect) asm volatile("mbarrier.arrive.shared::cluster.b64 _, [%0];" ::"r"(mapa(bars + 8 * B_RDY, rank ^ 1)) : "memory");
      fence_regs<0, 64>(ci);
#pragma unroll
      for (int i = 0; i < 16; i++) {
        const float gg = ((i & 1) ? g1 : g0) * (2.0f / (2048.0f * 512.0f));
        if (i & 2) yf[i] = pack_pin((ci[2 * i] - ci[28 + 2 * i]) * gg, (ci[2 * i + 1] - ci[29 + 2 * i]) * gg);
        else yf[i] = pack_pin((ci[2 * i] + ci[36 + 2 * i]) * gg, (ci[2 * i + 1] + ci[37 + 2 * i]) * gg);
      }
      rest(IC<0>(), 0);
      if (tid == 0) PROF_EV(8);
      head(IC<32>(), 1); freeT(0); mbar_wait(bars + 8 * B_RDY, 0); send_peer(IC<0>(), 0); rest(IC<32>(), 1);
      head(IC<0>(), 2); freeT(1); send_peer(IC<32>(), 1); rest(IC<0>(), 2);
      head(IC<32>(), 3); freeT(2); send_peer(IC<0>(), 2); rest(IC<32>(), 3);
      head(IC<0>(), 4); freeT(3); send_grid(IC<32>(), 0); rest(IC<0>(), 4);
      head(IC<32>(), 5); send_grid(IC<0>(), 1); rest(IC<32>(), 5);
      head(IC<0>(), 6); send_grid(IC<32>(), 2); rest(IC<0>(), 6);
      head(IC<32>(), 7); send_peer(IC<0>(), 3);
      {
        const uint4* src = g_part + (size_t)(rb * 8 + j) * 3 * 1024 + tid;
        uint4 pv[12];
        mbar_wait(bars + 8 * (B_HP + 1), 0);
#pragma unroll
        for (int i = 0; i < 8; i++) pv[i] = ld_x4(src + i * 256);
        rest(IC<32>(), 7);
        if (tid == 0) PROF_EV(9);
        mbar_wait(bars + 8 * (B_HP + 2), 0);
        if (tid == 0) PROF_EV(24);
#pragma unroll
        for (int i = 8; i < 12; i++) pv[i] = ld_x4(src + i * 256);
        const uint32_t t0 = (uint32_t)clock();
        for (;;) {
          uint32_t bad = 0;
#pragma unroll
          for (int i = 0; i < 12; i++) bad |= pv[i].x ^ tag;
          if (!__any_sync(0xffffffffu, bad & 1)) break;
#pragma unroll
          for (int i = 0; i < 12; i++) pv[i] = ld_x4(src + i * 256);
          spin_guard(t0);
        }
        if (tid == 0) PROF_EV(14);
        float sum[32];
#pragma unroll
        for (int i = 0; i < 4; i++) {
          const uint32_t a[4] = {pv[i].x & ~1u, pv[i].y, pv[i].z, pv[i].w}, b[4] = {pv[4 + i].x & ~1u, pv[4 + i].y, pv[4 + i].z, pv[4 + i].w},
                         c[4] = {pv[8 + i].x & ~1u, pv[8 + i].y, pv[8 + i].z, pv[8 + i].w};
#pragma unroll
          for (int e = 0; e < 4; e++) {
            sum[8 * i + 2 * e] = bf_lo(a[e]) + bf_lo(b[e]) + bf_lo(c[e]);
            sum[8 * i + 2 * e + 1] = bf_hi(a[e]) + bf_hi(b[e]) + bf_hi(c[e]);
          }
        }
        mbar_wait(bars + 8 * (B_Z + 3), 0);
#pragma unroll
        for (int i = 0; i < 4; i++) {
          const uint4 p = *(const uint4*)(smem + OFF_Z + 3 * U + i * 4096 + tid * 16);
          const uint32_t a[4] = {p.x, p.y, p.z, p.w};
#pragma unroll
          for (int e = 0; e < 4; e++) { sum[8 * i + 2 * e] += bf_lo(a[e]); sum[8 * i + 2 * e + 1] += bf_hi(a[e]); }
        }
        wg_wait<0>();
        fence_regs<32, 32>(ct);
#pragma unroll
        for (int i = 0; i < 32; i++) sum[i] += ct[32 + i];
        const uint32_t stg = sb + OFF_T + warp * 2048;
        const int mr = (lane & 7) + ((lane >> 3) & 1) * 8, mc = lane >> 4;
#pragma unroll
        for (int i = 0; i < 4; i++) {
          const uint32_t a = stg + mr * 128 + (((2 * i + mc) ^ (mr & 7)) << 4);
          asm volatile("stmatrix.sync.aligned.m8n8.x4.shared.b16 [%0], {%1,%2,%3,%4};" ::"r"(a), "r"(pack_bf16(sum[8 * i], sum[8 * i + 1])),
                       "r"(pack_bf16(sum[8 * i + 2], sum[8 * i + 3])), "r"(pack_bf16(sum[8 * i + 4], sum[8 * i + 5])),
                       "r"(pack_bf16(sum[8 * i + 6], sum[8 * i + 7])) : "memory");
        }
        __syncwarp();
#pragma unroll
        for (int i = 0; i < 4; i++) {
          const int r = 4 * i + (lane >> 3), c = lane & 7;
          const uint4 v = *(const uint4*)(smem + OFF_T + warp * 2048 + r * 128 + ((c ^ (r & 7)) << 4));
          *(uint4*)(out + (size_t)(2 * rb + wg + 32 * (16 * w + r)) * 512 + 64 * j + 8 * c) = v;
        }
      }
      if (tid == 0) { g_epoch[blockIdx.x * 8] = ep + 1; PROF_EV(15); PROF_CK(41); }
    }
  } else if (warp < 12) {
    asm volatile("setmaxnreg.dec.sync.aligned.u32 104;");
    asm volatile("barrier.cluster.arrive.relaxed.aligned;" ::: "memory");
    const int t = tid - 256, w = warp - 8;
    const uint32_t ep = ld_x1(&g_epoch[blockIdx.x * 8]);
    const uint32_t tag = (ep + 1) & 1;
    auto gate_rows = [&] {
      uint4 xv[8], gv[2];
#pragma unroll
      for (int i = 0; i < 4; i++) {
        const int r = 16 * j + 4 * w + i;
        const uint4* p = (const uint4*)(x + (size_t)(2 * rb + (r >> 6) + 32 * (r & 63)) * 512) + lane;
        xv[2 * i] = __ldg(p); xv[2 * i + 1] = __ldg(p + 32);
      }
      gv[0] = __ldg((const uint4*)gate_w + lane); gv[1] = __ldg((const uint4*)gate_w + lane + 32);
      {
        float z[4];
#pragma unroll
        for (int i = 0; i < 4; i++) {
          float a = 0.f;
#pragma unroll
          for (int hh = 0; hh < 2; hh++) {
            const uint4 u = xv[2 * i + hh], v = gv[hh];
            a = fmaf(bf_lo(u.x), bf_lo(v.x), a); a = fmaf(bf_hi(u.x), bf_hi(v.x), a);
            a = fmaf(bf_lo(u.y), bf_lo(v.y), a); a = fmaf(bf_hi(u.y), bf_hi(v.y), a);
            a = fmaf(bf_lo(u.z), bf_lo(v.z), a); a = fmaf(bf_hi(u.z), bf_hi(v.z), a);
            a = fmaf(bf_lo(u.w), bf_lo(v.w), a); a = fmaf(bf_hi(u.w), bf_hi(v.w), a);
          }
#pragma unroll
          for (int o = 16; o; o >>= 1) a += __shfl_xor_sync(0xffffffffu, a, o);
          z[i] = a;
        }
        if (lane < 4) {
          const float zz = lane == 0 ? z[0] : lane == 1 ? z[1] : lane == 2 ? z[2] : z[3];
          asm volatile("st.relaxed.gpu.global.f32 [%0], %1;" ::"l"(g_gate + rb * 128 + 16 * j + 4 * w + lane), "f"(tagf(1.0f / (1.0f + __expf(-zz)), tag)) : "memory");
        }
        if (t == 0) PROF_EV(18);
      }
      if (w == 0) {
        const int c = lane >> 4, jj = 16 * blockIdx.x + (lane & 15), jm = (2048 - jj) & 2047;
        const unsigned short* pr = (const unsigned short*)w_r + 256 * c;
        const unsigned short* pi = (const unsigned short*)w_i + 256 * c;
        const float wr = 0.25f * (bf_lo(__ldg(pr + jj * 257)) + bf_lo(__ldg(pr + jm * 257)));
        const float wi = 0.25f * (bf_lo(__ldg(pi + jj * 257)) - bf_lo(__ldg(pi + jm * 257)));
        st_u2(g_Wh + c * 2048 + jj, c ? pack_bf16(-wi, wr) : pack_bf16(wr, wi), tag);
        __syncwarp();
        if (lane == 0) hint_add(&g_cntW[0]);
      }
    };
    {
      const int g = lane >> 2, q = lane & 3;
      uint32_t wf[32];
      if (!helper) {
        gate_rows();
        asm volatile("bar.sync 4, 256;" ::: "memory");
        const uint32_t wa = sb + OFF_T + w * (3072 + 4) + q * 48 + g * 2;
        mbar_wait(bars + 8 * (B_FX + WAFTER), 0);
        if (t == 0) PROF_EV(32);
        __nanosleep(WPACE * w);
#pragma unroll
        for (int ri = 0; ri < 2; ri++) {
          if (lane == 0) {
            mbar_expect_tx(bars + 8 * (B_WR + w), 3072);
            tma4d(sb + OFF_T + w * 3072, ri ? &maps.wi : &maps.wr, bars + 8 * (B_WR + w), 16 * kg, 0, 2 * w, tn);
          }
          mbar_wait(bars + 8 * (B_WR + w), ri);
#pragma unroll
          for (int n2 = 0; n2 < 4; n2++) {
            uint32_t v[8];
#pragma unroll
            for (int i = 0; i < 8; i++)
              asm volatile("ld.shared.u16 %0, [%1];" : "=r"(v[i]) : "r"(wa + (2 * n2 + ((i >> 1) & 1)) * 192 + (i & 1) * (1536 + 2) + (i >> 2) * 16) : "memory");
#pragma unroll
            for (int i = 0; i < 8; i++) {
              uint32_t& d = wf[(i >> 2) * 16 + 4 * n2 + (i & 3)];
              d = ri ? d | (v[i] << 16) : v[i];
              asm volatile("" : "+r"(d)::"memory");
            }
          }
          __syncwarp();
        }
        asm volatile("bar.sync 1, 128;" ::: "memory");
        if (t == 0) PROF_EV(11);
      } else {
        asm volatile("bar.sync 4, 256;" ::: "memory");
        hint_wait(&g_cntW[0], (ep + 1) * 128u);
        const uint32_t t0 = (uint32_t)clock();
#pragma unroll 1
        for (;;) {
          uint32_t bad = 0;
#pragma unroll
          for (int i = 0; i < 32; i++) {
            const float2 v = ld_x2((const float2*)g_Wh + (i >> 4) * 2048 + 16 * w + g + 8 * (i & 1) + 64 * q + ((i >> 1) & 7) * 256);
            wf[i] = __float_as_uint(v.x); bad |= __float_as_uint(v.y) ^ tag;
          }
          if (!__any_sync(0xffffffffu, bad & 1)) break;
          spin_guard(t0);
        }
        if (t == 0) PROF_EV(11);
      }
      if (t == 0) { mbar_expect_tx(bars + 8 * B_W, 8192); bulk_load(sb + OFF_D, g_DT.v, 8192, bars + 8 * B_W); }
      mbar_wait(bars + 8 * B_W, 0);
      mbar_wait(bars + 8 * B_HX, 0);
      if (t == 0) PROF_EV(12);
      const uint32_t dd = (sb & 0x3FFFF) >> 4;
      const uint64_t dF = d128((dd + (OFF_D >> 4)) | (512u << 16)), dI = d128((dd + (OFF_D >> 4)) | (1u << 16)), dA = d128((dd + (OFF_XB >> 4)) | (512u << 16));
      float az[32];
      const int zero = blockIdx.x >> 16;
      uint32_t pf[32];
#pragma unroll
      for (int mt = 0; mt < 2; mt++) {
        wg_fence();
        if (mt == 0) mma_ss64<0, 3, 0>(az, dA, dF);
        else mma_ss64<0, 3, 2>(az, dA + 512, dF, zero);
#pragma unroll
        for (int k = 1; k < 4; k++) mma_ss64<0, 3, 1>(az, dA + (mt * 512 + k * 128), dF + k * 128);
        wg_commit();
        wg_wait<0>();
        fence_regs<0, 32>(az);
#pragma unroll
        for (int i = 0; i < 16; i++) {
          const float wr = bf_lo(wf[16 * mt + i]), wi = bf_hi(wf[16 * mt + i]);
          pf[16 * mt + i] = pack_pin(fmaf(az[2 * i], wr, -az[2 * i + 1] * wi), fmaf(az[2 * i], wi, az[2 * i + 1] * wr));
        }
      }
      if (t == 0) PROF_EV(16);
#pragma unroll
      for (int mt = 0; mt < 2; mt++) {
        wg_fence();
        mma_rs64<0, 0, 2>(az, pf[16 * mt], pf[16 * mt + 1], pf[16 * mt + 2], pf[16 * mt + 3], dI, mt ? (int)helper : zero);
#pragma unroll
        for (int k = 1; k < 4; k++) mma_rs64<0, 0, 1>(az, pf[16 * mt + 4 * k], pf[16 * mt + 4 * k + 1], pf[16 * mt + 4 * k + 2], pf[16 * mt + 4 * k + 3], dI + k * 2);
        wg_commit();
        wg_wait<0>();
        fence_regs<0, 32>(az);
        if (!helper) {
          const int m = lane >> 3, r = lane & 7;
          const int sl = 2 * (m >> 1) + ((r >> 1) & 1) + 4 * (r >> 2);
          const uint32_t a0 = sb + OFF_XB + (2 * w + (m & 1)) * 2048 + sl * 64 + (((mt * 2 + (r & 1)) ^ (sl >> 1)) << 4);
#pragma unroll
          for (int i = 0; i < 4; i++)
            stsm4t(a0 + i * 512, pack_bf16(az[8 * i], az[8 * i + 1]), pack_bf16(az[8 * i + 2], az[8 * i + 3]), pack_bf16(az[8 * i + 4], az[8 * i + 5]),
                   pack_bf16(az[8 * i + 6], az[8 * i + 7]));
        }
      }
      if (helper) {
#pragma unroll
        for (int i = 0; i < 16; i++) {
          const int n = i >> 1, s0 = 8 * (n >> 1) + 2 * (n & 1) + (q & 1) + 4 * (q >> 1);
          if ((n & 1) == (int)(blockIdx.x & 1)) st_u2(g_Ts + s0 * 64 + 16 * w + g + 8 * (i & 1), pack_bf16(az[2 * i], az[2 * i + 1]), tag);
        }
        __syncwarp();
        if (lane == 0) hint_add(&g_cntH[0]);
        if (t == 0) { g_epoch[blockIdx.x * 8] = ep + 1; PROF_EV(13); }
      } else {
        asm volatile("fence.proxy.async.shared::cta;" ::: "memory");
        asm volatile("bar.sync 1, 128;" ::: "memory");
        if (t == 0) {
          PROF_EV(17);
          asm volatile("cp.async.bulk.tensor.3d.global.shared::cta.bulk_group [%0, {%2, %3, %4}], [%1];" ::"l"(&maps.ts), "r"(sb + OFF_XB),
                       "r"(32 * kg), "r"(0), "r"(8 * tn) : "memory");
          bulk_done_signal(&g_cntT[32 * j]);
          PROF_EV(13);
        }
        __syncwarp();
        if (j == 0) {
          hint_wait(&g_cntH[0], (ep + 1) * 8u);
          const uint32_t t0 = (uint32_t)clock();
          float2 v;
          do { v = ld_x2((const float2*)g_Ts + 2 * rb * 64 + t); spin_guard(t0); } while (__any_sync(0xffffffffu, (__float_as_uint(v.y) ^ tag) & 1));
          mbar_wait(bars + 8 * B_TL, 0);
          const uint32_t u = __float_as_uint(v.x);
          *(uint16_t*)(smem + OFF_T + t * 128 + ((t & 7) << 4)) = (uint16_t)u;
          *(uint16_t*)(smem + OFF_T + t * 128 + (((t & 7) ^ 1) << 4)) = (uint16_t)(u >> 16);
          asm volatile("fence.proxy.async.shared::cta;" ::: "memory");
          __syncwarp();
          if (lane == 0) mbar_arrive(bars + 8 * B_T);
        }
      }
    }
  } else {
    asm volatile("setmaxnreg.dec.sync.aligned.u32 24;");
    if (warp < 14) {
      if (lane == 0) {
#pragma unroll
        for (int i = 0; i < 6; i++) mbar_init(bars + 8 * (2 * i + warp - 12), 1);
        asm volatile("fence.proxy.async.shared::cta;" ::: "memory");
      }
      __syncwarp();
      asm volatile("bar.arrive 0, 384;" ::: "memory");
      asm volatile("bar.arrive 4, 256;" ::: "memory");
      if (lane == 0) {
        if (!helper) {
#pragma unroll 1
          for (int n = warp - 12; n < NR; n += 2) {
            const uint32_t fb = bars + 8 * (B_FA + n), dst = sb + OFF_RING + n * U;
            x_load(n);
            mbar_expect_tx(fb, U);
            tma2d(dst, &maps.ft, fb, 64 * n, 64 * j);
            tma2d(dst + 8192, &maps.g32, fb, f_half, 64 * n);
            tma2d(dst + 12288, &maps.u32, fb, f_half, 64 * n);
          }
        }
      }
    } else {
      if (lane != 0) {
      } else if (warp == 15) {
#pragma unroll
        for (int i = B_FT; i < NBAR; i++) mbar_init(bars + 8 * i, i < B_EA ? 1 : i < B_T ? 2 : i < B_XS ? 4 : 8);
#pragma unroll
        for (int i = 0; i < 4; i++) mbar_expect_tx(bars + 8 * (B_Z + i), U);
        asm volatile("fence.mbarrier_init.release.cluster;" ::: "memory");
        asm volatile("fence.proxy.async.shared::cta;" ::: "memory");
      } else {
#pragma unroll
        for (int i = 1; i < 4; i++) asm volatile("prefetch.tensormap [%0];" ::"l"((const char*)&maps + i * 128) : "memory");
      }
      __syncwarp();
      asm volatile("bar.arrive 0, 384;" ::: "memory");
      asm volatile("bar.arrive 4, 256;" ::: "memory");
    }
    __syncwarp();
    asm volatile("barrier.cluster.arrive.relaxed.aligned;" ::: "memory");
    asm volatile("bar.sync 3, 128;" ::: "memory");
    if (lane == 0 && (!helper || warp == 15)) {
      if (warp < 14) {
        if (warp == 12) x_load(NR);
        int slot = 0, par = 0;
#pragma unroll 1
        for (int n = NR; n < 36; n++) {
          mbar_wait(bars + 8 * (B_EA + slot), par);
          ring_part(warp - 12, n, slot);
          if (warp == 12 && n < 7) x_load(n + 1);
          if (++slot == NR) { slot = 0; par ^= 1; }
        }
      } else if (warp == 15) {
        const unsigned ep1 = ld_x1(&g_epoch[blockIdx.x * 8]) + 1;
        flag_wait(&g_cntX[helper ? 0 : 32 * j], ep1 * 16u);
        PROF_EV(22);
        mbar_expect_tx(bars + 8 * B_HX, U);
        bulk_load(sb + OFF_XB, g_X + (size_t)(helper ? 128 : kg * 8 + tn) * 8192, U, bars + 8 * B_HX);
        if (!helper) {
          flag_wait(&g_cntT[32 * j], ep1 * 16u);
          PROF_EV(23);
          mbar_expect_tx(bars + 8 * B_TL, U);
          tma3d(sb + OFF_T, &maps.t, bars + 8 * B_TL, 64 * j, 0, 2 * rb);
#pragma unroll 1
          for (int i = 0; i < 3; i++) { hint_wait(&g_cntP[32 * (rb * 8 + j) + i], ep1 * 8u); mbar_arrive(bars + 8 * (B_HP + i)); }
        }
      } else {
#pragma unroll 1
        for (int i = 4; i < 14; i++) asm volatile("prefetch.tensormap [%0];" ::"l"((const char*)&maps + i * 128) : "memory");
        PROF_EV(31);
        mbar_wait(bars + 8 * B_XS, 0);
#pragma unroll
        for (int h2 = 0; h2 < 2; h2++) {
          const int s0 = 2 * rb + h2, sg = (s0 & ~6) | ((s0 & 2) << 1) | ((s0 & 4) >> 1);
          asm volatile("cp.async.bulk.tensor.4d.global.shared::cta.bulk_group [%0, {%2, %3, %4, %5}], [%1];" ::"l"(&maps.xs), "r"(sb + OFF_XB + h2 * 8192),
                       "r"(0), "r"(sg), "r"(0), "r"(16 * j) : "memory");
          if (j == 0) {
#pragma unroll
            for (int c = 0; c < 2; c++)
              asm volatile("cp.async.bulk.global.shared::cta.bulk_group [%0], [%1], 256;" ::"l"(g_X + 128 * 8192 + c * 4096 + sg * 128),
                           "r"(sb + OFF_SP + h2 * 512 + c * 256) : "memory");
          }
        }
        bulk_done_signal(&g_cntX[32 * j]);
        PROF_EV(20);
#pragma unroll 1
        for (int t = 0; t < 8; t++) {
          const int i = t < 3 ? t + 1 : t < 6 ? t - 2 : 0;
          const int col = 64 * (2 * ((q4 + i) & 3) + ((t < 3 || t == 6) ? 1 - rank : rank));
          const uint32_t fb = bars + 8 * (B_FT + (t & 3)), dst = sb + (t & 3) * TB;
          mbar_wait(bars + 8 * (B_ET + (t == 0 ? 1 : t & 3)), t >> 2);
          mbar_expect_tx(fb, TB);
          tma2d(dst, &maps.d192, fb, col, f_full);
          tma2d(dst + 24576, &maps.d32, fb, col, f_half);
          tma2d(dst + 28672, &maps.ft, fb, col, 64 * j);
        }
      }
    }
  }
}

typedef CUresult (*EncodeFn)(CUtensorMap*, CUtensorMapDataType, cuuint32_t, void*, const cuuint64_t*, const cuuint64_t*, const cuuint32_t*,
                             const cuuint32_t*, CUtensorMapInterleave, CUtensorMapSwizzle, CUtensorMapL2promotion, CUtensorMapFloatOOBfill);

static void encode(EncodeFn f, CUtensorMap* m, const void* base, int rank, const cuuint64_t* dims, const cuuint64_t* strides, const cuuint32_t* box,
                   CUtensorMapSwizzle sw) {
  cuuint32_t es[5] = {1, 1, 1, 1, 1};
  f(m, CU_TENSOR_MAP_DATA_TYPE_BFLOAT16, rank, (void*)base, dims, strides, box, es, CU_TENSOR_MAP_INTERLEAVE_NONE, sw,
    CU_TENSOR_MAP_L2_PROMOTION_L2_128B, CU_TENSOR_MAP_FLOAT_OOB_FILL_NONE);
}

extern "C" void kernel_launch(void* const* d_in, const int* in_sizes, int n_in, void* d_out, int out_size) {
  (void)in_sizes; (void)n_in; (void)out_size;
  const __nv_bfloat16* x = (const __nv_bfloat16*)d_in[0];
  const __nv_bfloat16* w_r = (const __nv_bfloat16*)d_in[1];
  const __nv_bfloat16* w_i = (const __nv_bfloat16*)d_in[2];
  const __nv_bfloat16* Wg = (const __nv_bfloat16*)d_in[4];
  const __nv_bfloat16* Wu = (const __nv_bfloat16*)d_in[5];
  const __nv_bfloat16* Wd = (const __nv_bfloat16*)d_in[6];
  const __nv_bfloat16* gw = (const __nv_bfloat16*)d_in[7];

  void* fp = nullptr; cudaDriverEntryPointQueryResult qr;
  cudaGetDriverEntryPoint("cuTensorMapEncodeTiled", &fp, cudaEnableDefault, &qr);
  EncodeFn enc = (EncodeFn)fp;
  void *pFT, *pET, *pX, *pT;
  cudaGetSymbolAddress(&pX, g_X); cudaGetSymbolAddress(&pT, g_T);
  cudaGetSymbolAddress(&pFT, g_FT); cudaGetSymbolAddress(&pET, g_ET);

  Maps mp;
  const CUtensorMapSwizzle S128 = CU_TENSOR_MAP_SWIZZLE_128B, S64 = CU_TENSOR_MAP_SWIZZLE_64B;
  { cuuint64_t d[3] = {512, 64, 32}, s[2] = {32768, 1024}; cuuint32_t b[3] = {64, 64, 2}; encode(enc, &mp.x, x, 3, d, s, b, S128); }
  { cuuint64_t d[2] = {512, 512}, s[1] = {1024}; cuuint32_t b[2] = {64, 64}; encode(enc, &mp.ft, pFT, 2, d, s, b, S128); }
  { cuuint64_t d[4] = {128, 32, 2, 129}, s[3] = {256, 8192, 16384}; cuuint32_t b[4] = {128, 1, 2, 16}; encode(enc, &mp.xs, pX, 4, d, s, b, CU_TENSOR_MAP_SWIZZLE_NONE); }
  { cuuint64_t d[3] = {512, 32, 64}, s[2] = {65536, 1024}; cuuint32_t b[3] = {32, 32, 8}; encode(enc, &mp.ts, pT, 3, d, s, b, S64); }
  { cuuint64_t d[3] = {512, 64, 32}, s[2] = {1024, 65536}; cuuint32_t b[3] = {64, 64, 2}; encode(enc, &mp.t, pT, 3, d, s, b, S128); }
  { cuuint64_t d[4] = {64, 64, 2, 32}, s[3] = {8192, 128, 256}; cuuint32_t b[4] = {64, 64, 2, 1}; encode(enc, &mp.e, pET, 4, d, s, b, S128); }
  { cuuint64_t d[2] = {1792, 512}, s[1] = {3584}; cuuint32_t b[2] = {64, 64}, b2[2] = {32, 64};
    encode(enc, &mp.g64, Wg, 2, d, s, b, S128); encode(enc, &mp.u64, Wu, 2, d, s, b, S128);
    encode(enc, &mp.g32, Wg, 2, d, s, b2, S64); encode(enc, &mp.u32, Wu, 2, d, s, b2, S64); }
  { cuuint64_t d[2] = {512, 1792}, s[1] = {1024}; cuuint32_t b[2] = {64, 192}, b2[2] = {64, 32};
    encode(enc, &mp.d192, Wd, 2, d, s, b, S128); encode(enc, &mp.d32, Wd, 2, d, s, b2, S128); }

  { cuuint64_t d[4] = {264, 32, 8, 8}, s[3] = {32896, 512, 4112}; cuuint32_t b[4] = {24, 32, 2, 1};
    encode(enc, &mp.wr, w_r, 4, d, s, b, CU_TENSOR_MAP_SWIZZLE_NONE); encode(enc, &mp.wi, w_i, 4, d, s, b, CU_TENSOR_MAP_SWIZZLE_NONE); }

  cudaFuncSetAttribute(fused_kernel, cudaFuncAttributeMaxDynamicSharedMemorySize, SMEM_BYTES);
  fused_kernel<<<NCTA, 512, SMEM_BYTES>>>(mp, x, w_r, w_i, gw, (__nv_bfloat16*)d_out);
}
```

```cpp
#include <cuda_runtime.h>
#include <cuda_bf16.h>
#include <cuda.h>
#include <stdint.h>

namespace tbl {
constexpr double PI = 3.14159265358979323846264338327950288;
constexpr double sin_s(double x) { double t = x, s = x; for (int n = 1; n < 12; n++) { t *= -x * x / ((2 * n) * (2 * n + 1)); s += t; } return s; }
constexpr double cos_s(double x) { double t = 1, s = 1; for (int n = 1; n < 12; n++) { t *= -x * x / ((2 * n - 1) * (2 * n)); s += t; } return s; }
constexpr double cos2048(int m) {
  m &= 2047; if (m > 1024) m = 2048 - m;
  bool neg = false; if (m > 512) { m = 1024 - m; neg = true; }
  double v = (m <= 256) ? cos_s(2 * PI * m / 2048) : sin_s(2 * PI * (512 - m) / 2048);
  return neg ? -v : v;
}
constexpr uint16_t to_bf16(double v) {
  if (v == 0) return 0;
  uint16_t s = 0; if (v < 0) { s = 0x8000; v = -v; }
  int e = 0; while (v >= 2) { v /= 2; e++; } while (v < 1) { v *= 2; e--; }
  double m = (v - 1) * 128; int mi = (int)m; double fr = m - mi;
  if (fr > 0.5 || (fr == 0.5 && (mi & 1))) mi++;
  if (mi == 128) { mi = 0; e++; }
  return (uint16_t)(s | ((e + 127) << 7) | mi);
}
struct CosT { uint16_t v[2048]; constexpr CosT() : v() { for (int i = 0; i < 2048; i++) v[i] = to_bf16(cos2048(i)); } };
struct alignas(1024) FT {
  uint16_t v[512 * 512];
  constexpr FT() : v() {
    CosT c;
    for (int r = 0; r < 512; r++) {
      int k = (r >> 4) * 8 + (r & 7), e = (r >> 3) & 1;
      int mul = 4 * k, add = e ? 512 : 0;
      if (k == 0 && e == 1) { mul = 1024; add = 0; }
      for (int d = 0; d < 512; d++) v[r * 512 + d] = c.v[(d * mul + add) & 2047];
    }
  }
};
struct alignas(1024) ET {
  uint16_t v[2048 * 128];
  constexpr ET() : v() {
    CosT c;
    for (int s = 0; s < 2048; s++)
      for (int j = 0; j < 64; j++) { v[s * 128 + j] = c.v[(s * j) & 2047]; v[s * 128 + 64 + j] = c.v[(s * j + 512) & 2047]; }
  }
};
struct alignas(1024) DT {
  uint16_t v[64 * 64];
  constexpr DT() : v() {
    CosT c;
    for (int r = 0; r < 64; r++)
      for (int n = 0; n < 64; n++) {
        const int sg = r >> 1, s0 = (sg & ~6) | ((sg & 2) << 1) | ((sg & 4) >> 1), e = r & 1, f = n & 1;
        const int m = 64 * s0 * (n >> 1) + (e == f ? 0 : e ? -512 : 512);
        v[r * 64 + (((n >> 3) ^ (r & 7)) << 3) + (n & 7)] = c.v[m & 2047];
      }
  }
};
}

__device__ constexpr tbl::FT g_FT = tbl::FT();
__device__ constexpr tbl::ET g_ET = tbl::ET();
__device__ constexpr tbl::DT g_DT = tbl::DT();

__device__ __align__(1024) uint16_t g_X[129 * 8192];
__device__ __align__(1024) uint16_t g_T[32 * 64 * 512];
__device__ __align__(1024) uint2 g_Ts[32 * 64];
__device__ __align__(1024) uint4 g_part[128 * 3 * 1024];
__device__ __align__(16) float g_gate[16 * 128];
__device__ __align__(16) uint2 g_Wh[2 * 2048];
__device__ unsigned g_epoch[132 * 8];
__device__ unsigned g_cntX[8 * 32], g_cntT[8 * 32], g_cntP[128 * 32], g_cntW[32], g_cntH[32];
#define PROF_EV(i) do {} while (0)
#define PROF_CK(i) do {} while (0)

__device__ __forceinline__ uint32_t smem_u32(const void* p) { return (uint32_t)__cvta_generic_to_shared(p); }
__device__ __forceinline__ void mbar_init(uint32_t bar, uint32_t cnt) { asm volatile("mbarrier.init.shared::cta.b64 [%0], %1;" ::"r"(bar), "r"(cnt)); }
__device__ __forceinline__ void mbar_expect_tx(uint32_t bar, uint32_t bytes) { asm volatile("mbarrier.arrive.expect_tx.shared::cta.b64 _, [%0], %1;" ::"r"(bar), "r"(bytes) : "memory"); }
__device__ __forceinline__ void mbar_arrive(uint32_t bar) { asm volatile("mbarrier.arrive.shared::cta.b64 _, [%0];" ::"r"(bar) : "memory"); }
__device__ __forceinline__ void mbar_wait(uint32_t bar, uint32_t parity) {
  asm volatile(
      "{\n.reg .pred p;\n.reg .u32 n;\nmov.u32 n, 0;\n"
      "W_LOOP:\nmbarrier.try_wait.parity.shared::cta.b64 p, [%0], %1;\n@p bra W_DONE;\n"
      "add.u32 n, n, 1;\nsetp.lt.u32 p, n, 0x40000;\n@p bra W_LOOP;\ntrap;\nW_DONE:\n}" ::"r"(bar), "r"(parity) : "memory");
}
__device__ __forceinline__ void bulk_load(uint32_t dst, const void* src, uint32_t bytes, uint32_t bar) {
  asm volatile("cp.async.bulk.shared::cluster.global.mbarrier::complete_tx::bytes [%0], [%1], %2, [%3];" ::"r"(dst), "l"(src), "r"(bytes), "r"(bar) : "memory");
}
__device__ __forceinline__ void cp16(uint32_t dst, const void* src) { asm volatile("cp.async.cg.shared.global [%0], [%1], 16;" ::"r"(dst), "l"(src) : "memory"); }
__device__ __forceinline__ void spin_guard(uint32_t t0) { if ((uint32_t)clock() - t0 > (1u << 30)) __trap(); }
__device__ __forceinline__ float tagf(float v, uint32_t tag) { return __uint_as_float((__float_as_uint(v) & ~1u) | tag); }
__device__ __forceinline__ float untag(float v) { return __uint_as_float(__float_as_uint(v) & ~1u); }
__device__ __forceinline__ void st_x2(float2* p, float a, float b) { asm volatile("st.relaxed.gpu.global.v2.f32 [%0], {%1,%2};" ::"l"(p), "f"(a), "f"(b) : "memory"); }
__device__ __forceinline__ float2 ld_x2(const float2* p) { float2 v; asm volatile("ld.relaxed.gpu.global.v2.f32 {%0,%1}, [%2];" : "=f"(v.x), "=f"(v.y) : "l"(p) : "memory"); return v; }
__device__ __forceinline__ void st_u2(uint2* p, uint32_t a, uint32_t b) { asm volatile("st.relaxed.gpu.global.v2.u32 [%0], {%1,%2};" ::"l"(p), "r"(a), "r"(b) : "memory"); }
__device__ __forceinline__ void prefetch2d(const CUtensorMap* m, int c0, int c1) { asm volatile("cp.async.bulk.prefetch.tensor.2d.L2.global [%0, {%1, %2}];" ::"l"(m), "r"(c0), "r"(c1) : "memory"); }
__device__ __forceinline__ void prefetch1d(const void* p, uint32_t bytes) { asm volatile("cp.async.bulk.prefetch.L2.global [%0], %1;" ::"l"(p), "r"(bytes) : "memory"); }
__device__ __forceinline__ uint32_t ld_x1(const void* p) { uint32_t v; asm volatile("ld.relaxed.gpu.global.u32 %0, [%1];" : "=r"(v) : "l"(p) : "memory"); return v; }
__device__ __forceinline__ uint4 ld_x4(const void* p) { uint4 v; asm volatile("ld.relaxed.gpu.global.v4.u32 {%0,%1,%2,%3}, [%4];" : "=r"(v.x), "=r"(v.y), "=r"(v.z), "=r"(v.w) : "l"(p) : "memory"); return v; }
__device__ __forceinline__ void st_x4(void* p, uint32_t a, uint32_t b, uint32_t c, uint32_t d) { asm volatile("st.relaxed.gpu.global.v4.u32 [%0], {%1,%2,%3,%4};" ::"l"(p), "r"(a), "r"(b), "r"(c), "r"(d) : "memory"); }
__device__ __forceinline__ uint32_t mapa(uint32_t a, uint32_t cta) { uint32_t r; asm volatile("mapa.shared::cluster.u32 %0, %1, %2;" : "=r"(r) : "r"(a), "r"(cta)); return r; }
__device__ __forceinline__ void stsm4t(uint32_t a, uint32_t r0, uint32_t r1, uint32_t r2, uint32_t r3) {
  asm volatile("stmatrix.sync.aligned.m8n8.x4.trans.shared.b16 [%0], {%1,%2,%3,%4};" ::"r"(a), "r"(r0), "r"(r1), "r"(r2), "r"(r3) : "memory");
}
__device__ __forceinline__ void hint_add(unsigned* p) { asm volatile("red.relaxed.gpu.global.add.u32 [%0], 1;" ::"l"(p) : "memory"); }
__device__ __forceinline__ void hint_wait(const unsigned* p, unsigned target) {
  const uint32_t t0 = (uint32_t)clock();
  while ((int)(ld_x1(p) - target) < 0) spin_guard(t0);
}
__device__ __forceinline__ void bulk_done_signal(unsigned* p) {
  asm volatile("cp.async.bulk.commit_group;\ncp.async.bulk.wait_group 0;\nfence.proxy.async.global;" ::: "memory");
  hint_add(p);
}
__device__ __forceinline__ void flag_wait(const unsigned* p, unsigned target) {
  hint_wait(p, target);
  asm volatile("fence.proxy.async.global;" ::: "memory");
}
__device__ __forceinline__ void tma2d(uint32_t dst, const CUtensorMap* m, uint32_t bar, int c0, int c1) {
  asm volatile("cp.async.bulk.tensor.2d.shared::cluster.global.mbarrier::complete_tx::bytes [%0], [%1, {%3, %4}], [%2];" ::"r"(dst), "l"(m), "r"(bar), "r"(c0), "r"(c1) : "memory");
}
__device__ __forceinline__ void tma3d(uint32_t dst, const CUtensorMap* m, uint32_t bar, int c0, int c1, int c2) {
  asm volatile("cp.async.bulk.tensor.3d.shared::cluster.global.mbarrier::complete_tx::bytes [%0], [%1, {%3, %4, %5}], [%2];" ::"r"(dst), "l"(m), "r"(bar), "r"(c0), "r"(c1), "r"(c2) : "memory");
}
__device__ __forceinline__ void tma4d(uint32_t dst, const CUtensorMap* m, uint32_t bar, int c0, int c1, int c2, int c3) {
  asm volatile("cp.async.bulk.tensor.4d.shared::cluster.global.mbarrier::complete_tx::bytes [%0], [%1, {%3, %4, %5, %6}], [%2];" ::"r"(dst), "l"(m), "r"(bar), "r"(c0), "r"(c1), "r"(c2), "r"(c3) : "memory");
}
__device__ __forceinline__ void wg_fence() { asm volatile("wgmma.fence.sync.aligned;" ::: "memory"); }
__device__ __forceinline__ void wg_commit() { asm volatile("wgmma.commit_group.sync.aligned;" ::: "memory"); }
template <int N> __device__ __forceinline__ void wg_wait() { asm volatile("wgmma.wait_group.sync.aligned %0;" ::"n"(N) : "memory"); }
template <int O, int N, int NN> __device__ __forceinline__ void fence_regs(float (&d)[NN]) {
#pragma unroll
  for (int i = 0; i < N; i++) asm volatile("" : "+f"(d[O + i])::"memory");
}
__device__ __forceinline__ uint32_t pack_bf16(float lo, float hi) {
  uint32_t r; asm("cvt.rn.bf16x2.f32 %0, %1, %2;" : "=r"(r) : "f"(hi), "f"(lo)); return r;
}
__device__ __forceinline__ uint32_t pack_pin(float lo, float hi) {
  uint32_t r; asm volatile("cvt.rn.bf16x2.f32 %0, %1, %2;" : "=r"(r) : "f"(hi), "f"(lo) : "memory"); return r;
}
__device__ __forceinline__ float bf_lo(uint32_t u) { return __uint_as_float(u << 16); }
__device__ __forceinline__ float bf_hi(uint32_t u) { return __uint_as_float(u & 0xffff0000u); }

__device__ __forceinline__ uint64_t d128(uint32_t lo) { uint64_t d; asm("mov.b64 %0, {%1, 0x40000040};" : "=l"(d) : "r"(lo)); return d; }
__device__ __forceinline__ uint64_t d64(uint32_t lo) { uint64_t d; asm("mov.b64 %0, {%1, 0x80000020};" : "=l"(d) : "r"(lo)); return d; }
template<int O,int TB,int ACC,int NN> __device__ __forceinline__ void mma_ss64(float (&d)[NN], uint64_t da, uint64_t db, int sd = 0){
  if constexpr (ACC == 1) asm volatile("wgmma.mma_async.sync.aligned.m64n64k16.f32.bf16.bf16 {%0,%1,%2,%3,%4,%5,%6,%7,%8,%9,%10,%11,%12,%13,%14,%15,%16,%17,%18,%19,%20,%21,%22,%23,%24,%25,%26,%27,%28,%29,%30,%31}, %32, %33, 1, 1, 1, %35, %34;"
   : "+f"(d[O+0]), "+f"(d[O+1]), "+f"(d[O+2]), "+f"(d[O+3]), "+f"(d[O+4]), "+f"(d[O+5]), "+f"(d[O+6]), "+f"(d[O+7]), "+f"(d[O+8]), "+f"(d[O+9]), "+f"(d[O+10]), "+f"(d[O+11]), "+f"(d[O+12]), "+f"(d[O+13]), "+f"(d[O+14]), "+f"(d[O+15]), "+f"(d[O+16]), "+f"(d[O+17]), "+f"(d[O+18]), "+f"(d[O+19]), "+f"(d[O+20]), "+f"(d[O+21]), "+f"(d[O+22]), "+f"(d[O+23]), "+f"(d[O+24]), "+f"(d[O+25]), "+f"(d[O+26]), "+f"(d[O+27]), "+f"(d[O+28]), "+f"(d[O+29]), "+f"(d[O+30]), "+f"(d[O+31])
   : "l"(da), "l"(db), "n"(TB & 1), "n"(TB >> 1));
  else if constexpr (ACC == 0) asm volatile("wgmma.mma_async.sync.aligned.m64n64k16.f32.bf16.bf16 {%0,%1,%2,%3,%4,%5,%6,%7,%8,%9,%10,%11,%12,%13,%14,%15,%16,%17,%18,%19,%20,%21,%22,%23,%24,%25,%26,%27,%28,%29,%30,%31}, %32, %33, 0, 1, 1, %35, %34;"
   : "=f"(d[O+0]), "=f"(d[O+1]), "=f"(d[O+2]), "=f"(d[O+3]), "=f"(d[O+4]), "=f"(d[O+5]), "=f"(d[O+6]), "=f"(d[O+7]), "=f"(d[O+8]), "=f"(d[O+9]), "=f"(d[O+10]), "=f"(d[O+11]), "=f"(d[O+12]), "=f"(d[O+13]), "=f"(d[O+14]), "=f"(d[O+15]), "=f"(d[O+16]), "=f"(d[O+17]), "=f"(d[O+18]), "=f"(d[O+19]), "=f"(d[O+20]), "=f"(d[O+21]), "=f"(d[O+22]), "=f"(d[O+23]), "=f"(d[O+24]), "=f"(d[O+25]), "=f"(d[O+26]), "=f"(d[O+27]), "=f"(d[O+28]), "=f"(d[O+29]), "=f"(d[O+30]), "=f"(d[O+31])
   : "l"(da), "l"(db), "n"(TB & 1), "n"(TB >> 1));
  else asm volatile("{\n.reg .pred p;\nsetp.ne.b32 p, %36, 0;\nwgmma.mma_async.sync.aligned.m64n64k16.f32.bf16.bf16 {%0,%1,%2,%3,%4,%5,%6,%7,%8,%9,%10,%11,%12,%13,%14,%15,%16,%17,%18,%19,%20,%21,%22,%23,%24,%25,%26,%27,%28,%29,%30,%31}, %32, %33, p, 1, 1, %35, %34;\n}"
   : "+f"(d[O+0]), "+f"(d[O+1]), "+f"(d[O+2]), "+f"(d[O+3]), "+f"(d[O+4]), "+f"(d[O+5]), "+f"(d[O+6]), "+f"(d[O+7]), "+f"(d[O+8]), "+f"(d[O+9]), "+f"(d[O+10]), "+f"(d[O+11]), "+f"(d[O+12]), "+f"(d[O+13]), "+f"(d[O+14]), "+f"(d[O+15]), "+f"(d[O+16]), "+f"(d[O+17]), "+f"(d[O+18]), "+f"(d[O+19]), "+f"(d[O+20]), "+f"(d[O+21]), "+f"(d[O+22]), "+f"(d[O+23]), "+f"(d[O+24]), "+f"(d[O+25]), "+f"(d[O+26]), "+f"(d[O+27]), "+f"(d[O+28]), "+f"(d[O+29]), "+f"(d[O+30]), "+f"(d[O+31])
   : "l"(da), "l"(db), "n"(TB & 1), "n"(TB >> 1), "r"(sd));
}
template<int O,int TB,int ACC,int NN> __device__ __forceinline__ void mma_rs64(float (&d)[NN], uint32_t a0, uint32_t a1, uint32_t a2, uint32_t a3, uint64_t db, int sd = 0){
  if constexpr (ACC == 1) asm volatile("wgmma.mma_async.sync.aligned.m64n64k16.f32.bf16.bf16 {%0,%1,%2,%3,%4,%5,%6,%7,%8,%9,%10,%11,%12,%13,%14,%15,%16,%17,%18,%19,%20,%21,%22,%23,%24,%25,%26,%27,%28,%29,%30,%31}, {%32,%33,%34,%35}, %36, 1, 1, 1, %37;"
   : "+f"(d[O+0]), "+f"(d[O+1]), "+f"(d[O+2]), "+f"(d[O+3]), "+f"(d[O+4]), "+f"(d[O+5]), "+f"(d[O+6]), "+f"(d[O+7]), "+f"(d[O+8]), "+f"(d[O+9]), "+f"(d[O+10]), "+f"(d[O+11]), "+f"(d[O+12]), "+f"(d[O+13]), "+f"(d[O+14]), "+f"(d[O+15]), "+f"(d[O+16]), "+f"(d[O+17]), "+f"(d[O+18]), "+f"(d[O+19]), "+f"(d[O+20]), "+f"(d[O+21]), "+f"(d[O+22]), "+f"(d[O+23]), "+f"(d[O+24]), "+f"(d[O+25]), "+f"(d[O+26]), "+f"(d[O+27]), "+f"(d[O+28]), "+f"(d[O+29]), "+f"(d[O+30]), "+f"(d[O+31])
   : "r"(a0), "r"(a1), "r"(a2), "r"(a3), "l"(db), "n"(TB));
  else if constexpr (ACC == 0) asm volatile("wgmma.mma_async.sync.aligned.m64n64k16.f32.bf16.bf16 {%0,%1,%2,%3,%4,%5,%6,%7,%8,%9,%10,%11,%12,%13,%14,%15,%16,%17,%18,%19,%20,%21,%22,%23,%24,%25,%26,%27,%28,%29,%30,%31}, {%32,%33,%34,%35}, %36, 0, 1, 1, %37;"
   : "=f"(d[O+0]), "=f"(d[O+1]), "=f"(d[O+2]), "=f"(d[O+3]), "=f"(d[O+4]), "=f"(d[O+5]), "=f"(d[O+6]), "=f"(d[O+7]), "=f"(d[O+8]), "=f"(d[O+9]), "=f"(d[O+10]), "=f"(d[O+11]), "=f"(d[O+12]), "=f"(d[O+13]), "=f"(d[O+14]), "=f"(d[O+15]), "=f"(d[O+16]), "=f"(d[O+17]), "=f"(d[O+18]), "=f"(d[O+19]), "=f"(d[O+20]), "=f"(d[O+21]), "=f"(d[O+22]), "=f"(d[O+23]), "=f"(d[O+24]), "=f"(d[O+25]), "=f"(d[O+26]), "=f"(d[O+27]), "=f"(d[O+28]), "=f"(d[O+29]), "=f"(d[O+30]), "=f"(d[O+31])
   : "r"(a0), "r"(a1), "r"(a2), "r"(a3), "l"(db), "n"(TB));
  else asm volatile("{\n.reg .pred p;\nsetp.ne.b32 p, %38, 0;\nwgmma.mma_async.sync.aligned.m64n64k16.f32.bf16.bf16 {%0,%1,%2,%3,%4,%5,%6,%7,%8,%9,%10,%11,%12,%13,%14,%15,%16,%17,%18,%19,%20,%21,%22,%23,%24,%25,%26,%27,%28,%29,%30,%31}, {%32,%33,%34,%35}, %36, p, 1, 1, %37;\n}"
   : "+f"(d[O+0]), "+f"(d[O+1]), "+f"(d[O+2]), "+f"(d[O+3]), "+f"(d[O+4]), "+f"(d[O+5]), "+f"(d[O+6]), "+f"(d[O+7]), "+f"(d[O+8]), "+f"(d[O+9]), "+f"(d[O+10]), "+f"(d[O+11]), "+f"(d[O+12]), "+f"(d[O+13]), "+f"(d[O+14]), "+f"(d[O+15]), "+f"(d[O+16]), "+f"(d[O+17]), "+f"(d[O+18]), "+f"(d[O+19]), "+f"(d[O+20]), "+f"(d[O+21]), "+f"(d[O+22]), "+f"(d[O+23]), "+f"(d[O+24]), "+f"(d[O+25]), "+f"(d[O+26]), "+f"(d[O+27]), "+f"(d[O+28]), "+f"(d[O+29]), "+f"(d[O+30]), "+f"(d[O+31])
   : "r"(a0), "r"(a1), "r"(a2), "r"(a3), "l"(db), "n"(TB), "r"(sd));
}
template<int O,int TB,int ACC,int NN> __device__ __forceinline__ void mma_ss128(float (&d)[NN], uint64_t da, uint64_t db, int sd = 0){
  if constexpr (ACC == 1) asm volatile("wgmma.mma_async.sync.aligned.m64n128k16.f32.bf16.bf16 {%0,%1,%2,%3,%4,%5,%6,%7,%8,%9,%10,%11,%12,%13,%14,%15,%16,%17,%18,%19,%20,%21,%22,%23,%24,%25,%26,%27,%28,%29,%30,%31,%32,%33,%34,%35,%36,%37,%38,%39,%40,%41,%42,%43,%44,%45,%46,%47,%48,%49,%50,%51,%52,%53,%54,%55,%56,%57,%58,%59,%60,%61,%62,%63}, %64, %65, 1, 1, 1, %67, %66;"
   : "+f"(d[O+0]), "+f"(d[O+1]), "+f"(d[O+2]), "+f"(d[O+3]), "+f"(d[O+4]), "+f"(d[O+5]), "+f"(d[O+6]), "+f"(d[O+7]), "+f"(d[O+8]), "+f"(d[O+9]), "+f"(d[O+10]), "+f"(d[O+11]), "+f"(d[O+12]), "+f"(d[O+13]), "+f"(d[O+14]), "+f"(d[O+15]), "+f"(d[O+16]), "+f"(d[O+17]), "+f"(d[O+18]), "+f"(d[O+19]), "+f"(d[O+20]), "+f"(d[O+21]), "+f"(d[O+22]), "+f"(d[O+23]), "+f"(d[O+24]), "+f"(d[O+25]), "+f"(d[O+26]), "+f"(d[O+27]), "+f"(d[O+28]), "+f"(d[O+29]), "+f"(d[O+30]), "+f"(d[O+31]), "+f"(d[O+32]), "+f"(d[O+33]), "+f"(d[O+34]), "+f"(d[O+35]), "+f"(d[O+36]), "+f"(d[O+37]), "+f"(d[O+38]), "+f"(d[O+39]), "+f"(d[O+40]), "+f"(d[O+41]), "+f"(d[O+42]), "+f"(d[O+43]), "+f"(d[O+44]), "+f"(d[O+45]), "+f"(d[O+46]), "+f"(d[O+47]), "+f"(d[O+48]), "+f"(d[O+49]), "+f"(d[O+50]), "+f"(d[O+51]), "+f"(d[O+52]), "+f"(d[O+53]), "+f"(d[O+54]), "+f"(d[O+55]), "+f"(d[O+56]), "+f"(d[O+57]), "+f"(d[O+58]), "+f"(d[O+59]), "+f"(d[O+60]), "+f"(d[O+61]), "+f"(d[O+62]), "+f"(d[O+63])
   : "l"(da), "l"(db), "n"(TB & 1), "n"(TB >> 1));
  else if constexpr (ACC == 0) asm volatile("wgmma.mma_async.sync.aligned.m64n128k16.f32.bf16.bf16 {%0,%1,%2,%3,%4,%5,%6,%7,%8,%9,%10,%11,%12,%13,%14,%15,%16,%17,%18,%19,%20,%21,%22,%23,%24,%25,%26,%27,%28,%29,%30,%31,%32,%33,%34,%35,%36,%37,%38,%39,%40,%41,%42,%43,%44,%45,%46,%47,%48,%49,%50,%51,%52,%53,%54,%55,%56,%57,%58,%59,%60,%61,%62,%63}, %64, %65, 0, 1, 1, %67, %66;"
   : "=f"(d[O+0]), "=f"(d[O+1]), "=f"(d[O+2]), "=f"(d[O+3]), "=f"(d[O+4]), "=f"(d[O+5]), "=f"(d[O+6]), "=f"(d[O+7]), "=f"(d[O+8]), "=f"(d[O+9]), "=f"(d[O+10]), "=f"(d[O+11]), "=f"(d[O+12]), "=f"(d[O+13]), "=f"(d[O+14]), "=f"(d[O+15]), "=f"(d[O+16]), "=f"(d[O+17]), "=f"(d[O+18]), "=f"(d[O+19]), "=f"(d[O+20]), "=f"(d[O+21]), "=f"(d[O+22]), "=f"(d[O+23]), "=f"(d[O+24]), "=f"(d[O+25]), "=f"(d[O+26]), "=f"(d[O+27]), "=f"(d[O+28]), "=f"(d[O+29]), "=f"(d[O+30]), "=f"(d[O+31]), "=f"(d[O+32]), "=f"(d[O+33]), "=f"(d[O+34]), "=f"(d[O+35]), "=f"(d[O+36]), "=f"(d[O+37]), "=f"(d[O+38]), "=f"(d[O+39]), "=f"(d[O+40]), "=f"(d[O+41]), "=f"(d[O+42]), "=f"(d[O+43]), "=f"(d[O+44]), "=f"(d[O+45]), "=f"(d[O+46]), "=f"(d[O+47]), "=f"(d[O+48]), "=f"(d[O+49]), "=f"(d[O+50]), "=f"(d[O+51]), "=f"(d[O+52]), "=f"(d[O+53]), "=f"(d[O+54]), "=f"(d[O+55]), "=f"(d[O+56]), "=f"(d[O+57]), "=f"(d[O+58]), "=f"(d[O+59]), "=f"(d[O+60]), "=f"(d[O+61]), "=f"(d[O+62]), "=f"(d[O+63])
   : "l"(da), "l"(db), "n"(TB & 1), "n"(TB >> 1));
  else asm volatile("{\n.reg .pred p;\nsetp.ne.b32 p, %68, 0;\nwgmma.mma_async.sync.aligned.m64n128k16.f32.bf16.bf16 {%0,%1,%2,%3,%4,%5,%6,%7,%8,%9,%10,%11,%12,%13,%14,%15,%16,%17,%18,%19,%20,%21,%22,%23,%24,%25,%26,%27,%28,%29,%30,%31,%32,%33,%34,%35,%36,%37,%38,%39,%40,%41,%42,%43,%44,%45,%46,%47,%48,%49,%50,%51,%52,%53,%54,%55,%56,%57,%58,%59,%60,%61,%62,%63}, %64, %65, p, 1, 1, %67, %66;\n}"
   : "+f"(d[O+0]), "+f"(d[O+1]), "+f"(d[O+2]), "+f"(d[O+3]), "+f"(d[O+4]), "+f"(d[O+5]), "+f"(d[O+6]), "+f"(d[O+7]), "+f"(d[O+8]), "+f"(d[O+9]), "+f"(d[O+10]), "+f"(d[O+11]), "+f"(d[O+12]), "+f"(d[O+13]), "+f"(d[O+14]), "+f"(d[O+15]), "+f"(d[O+16]), "+f"(d[O+17]), "+f"(d[O+18]), "+f"(d[O+19]), "+f"(d[O+20]), "+f"(d[O+21]), "+f"(d[O+22]), "+f"(d[O+23]), "+f"(d[O+24]), "+f"(d[O+25]), "+f"(d[O+26]), "+f"(d[O+27]), "+f"(d[O+28]), "+f"(d[O+29]), "+f"(d[O+30]), "+f"(d[O+31]), "+f"(d[O+32]), "+f"(d[O+33]), "+f"(d[O+34]), "+f"(d[O+35]), "+f"(d[O+36]), "+f"(d[O+37]), "+f"(d[O+38]), "+f"(d[O+39]), "+f"(d[O+40]), "+f"(d[O+41]), "+f"(d[O+42]), "+f"(d[O+43]), "+f"(d[O+44]), "+f"(d[O+45]), "+f"(d[O+46]), "+f"(d[O+47]), "+f"(d[O+48]), "+f"(d[O+49]), "+f"(d[O+50]), "+f"(d[O+51]), "+f"(d[O+52]), "+f"(d[O+53]), "+f"(d[O+54]), "+f"(d[O+55]), "+f"(d[O+56]), "+f"(d[O+57]), "+f"(d[O+58]), "+f"(d[O+59]), "+f"(d[O+60]), "+f"(d[O+61]), "+f"(d[O+62]), "+f"(d[O+63])
   : "l"(da), "l"(db), "n"(TB & 1), "n"(TB >> 1), "r"(sd));
}
template<int O,int TB,int ACC,int NN> __device__ __forceinline__ void mma_rs128(float (&d)[NN], uint32_t a0, uint32_t a1, uint32_t a2, uint32_t a3, uint64_t db, int sd = 0){
  if constexpr (ACC == 1) asm volatile("wgmma.mma_async.sync.aligned.m64n128k16.f32.bf16.bf16 {%0,%1,%2,%3,%4,%5,%6,%7,%8,%9,%10,%11,%12,%13,%14,%15,%16,%17,%18,%19,%20,%21,%22,%23,%24,%25,%26,%27,%28,%29,%30,%31,%32,%33,%34,%35,%36,%37,%38,%39,%40,%41,%42,%43,%44,%45,%46,%47,%48,%49,%50,%51,%52,%53,%54,%55,%56,%57,%58,%59,%60,%61,%62,%63}, {%64,%65,%66,%67}, %68, 1, 1, 1, %69;"
   : "+f"(d[O+0]), "+f"(d[O+1]), "+f"(d[O+2]), "+f"(d[O+3]), "+f"(d[O+4]), "+f"(d[O+5]), "+f"(d[O+6]), "+f"(d[O+7]), "+f"(d[O+8]), "+f"(d[O+9]), "+f"(d[O+10]), "+f"(d[O+11]), "+f"(d[O+12]), "+f"(d[O+13]), "+f"(d[O+14]), "+f"(d[O+15]), "+f"(d[O+16]), "+f"(d[O+17]), "+f"(d[O+18]), "+f"(d[O+19]), "+f"(d[O+20]), "+f"(d[O+21]), "+f"(d[O+22]), "+f"(d[O+23]), "+f"(d[O+24]), "+f"(d[O+25]), "+f"(d[O+26]), "+f"(d[O+27]), "+f"(d[O+28]), "+f"(d[O+29]), "+f"(d[O+30]), "+f"(d[O+31]), "+f"(d[O+32]), "+f"(d[O+33]), "+f"(d[O+34]), "+f"(d[O+35]), "+f"(d[O+36]), "+f"(d[O+37]), "+f"(d[O+38]), "+f"(d[O+39]), "+f"(d[O+40]), "+f"(d[O+41]), "+f"(d[O+42]), "+f"(d[O+43]), "+f"(d[O+44]), "+f"(d[O+45]), "+f"(d[O+46]), "+f"(d[O+47]), "+f"(d[O+48]), "+f"(d[O+49]), "+f"(d[O+50]), "+f"(d[O+51]), "+f"(d[O+52]), "+f"(d[O+53]), "+f"(d[O+54]), "+f"(d[O+55]), "+f"(d[O+56]), "+f"(d[O+57]), "+f"(d[O+58]), "+f"(d[O+59]), "+f"(d[O+60]), "+f"(d[O+61]), "+f"(d[O+62]), "+f"(d[O+63])
   : "r"(a0), "r"(a1), "r"(a2), "r"(a3), "l"(db), "n"(TB));
  else if constexpr (ACC == 0) asm volatile("wgmma.mma_async.sync.aligned.m64n128k16.f32.bf16.bf16 {%0,%1,%2,%3,%4,%5,%6,%7,%8,%9,%10,%11,%12,%13,%14,%15,%16,%17,%18,%19,%20,%21,%22,%23,%24,%25,%26,%27,%28,%29,%30,%31,%32,%33,%34,%35,%36,%37,%38,%39,%40,%41,%42,%43,%44,%45,%46,%47,%48,%49,%50,%51,%52,%53,%54,%55,%56,%57,%58,%59,%60,%61,%62,%63}, {%64,%65,%66,%67}, %68, 0, 1, 1, %69;"
   : "=f"(d[O+0]), "=f"(d[O+1]), "=f"(d[O+2]), "=f"(d[O+3]), "=f"(d[O+4]), "=f"(d[O+5]), "=f"(d[O+6]), "=f"(d[O+7]), "=f"(d[O+8]), "=f"(d[O+9]), "=f"(d[O+10]), "=f"(d[O+11]), "=f"(d[O+12]), "=f"(d[O+13]), "=f"(d[O+14]), "=f"(d[O+15]), "=f"(d[O+16]), "=f"(d[O+17]), "=f"(d[O+18]), "=f"(d[O+19]), "=f"(d[O+20]), "=f"(d[O+21]), "=f"(d[O+22]), "=f"(d[O+23]), "=f"(d[O+24]), "=f"(d[O+25]), "=f"(d[O+26]), "=f"(d[O+27]), "=f"(d[O+28]), "=f"(d[O+29]), "=f"(d[O+30]), "=f"(d[O+31]), "=f"(d[O+32]), "=f"(d[O+33]), "=f"(d[O+34]), "=f"(d[O+35]), "=f"(d[O+36]), "=f"(d[O+37]), "=f"(d[O+38]), "=f"(d[O+39]), "=f"(d[O+40]), "=f"(d[O+41]), "=f"(d[O+42]), "=f"(d[O+43]), "=f"(d[O+44]), "=f"(d[O+45]), "=f"(d[O+46]), "=f"(d[O+47]), "=f"(d[O+48]), "=f"(d[O+49]), "=f"(d[O+50]), "=f"(d[O+51]), "=f"(d[O+52]), "=f"(d[O+53]), "=f"(d[O+54]), "=f"(d[O+55]), "=f"(d[O+56]), "=f"(d[O+57]), "=f"(d[O+58]), "=f"(d[O+59]), "=f"(d[O+60]), "=f"(d[O+61]), "=f"(d[O+62]), "=f"(d[O+63])
   : "r"(a0), "r"(a1), "r"(a2), "r"(a3), "l"(db), "n"(TB));
  else asm volatile("{\n.reg .pred p;\nsetp.ne.b32 p, %70, 0;\nwgmma.mma_async.sync.aligned.m64n128k16.f32.bf16.bf16 {%0,%1,%2,%3,%4,%5,%6,%7,%8,%9,%10,%11,%12,%13,%14,%15,%16,%17,%18,%19,%20,%21,%22,%23,%24,%25,%26,%27,%28,%29,%30,%31,%32,%33,%34,%35,%36,%37,%38,%39,%40,%41,%42,%43,%44,%45,%46,%47,%48,%49,%50,%51,%52,%53,%54,%55,%56,%57,%58,%59,%60,%61,%62,%63}, {%64,%65,%66,%67}, %68, p, 1, 1, %69;\n}"
   : "+f"(d[O+0]), "+f"(d[O+1]), "+f"(d[O+2]), "+f"(d[O+3]), "+f"(d[O+4]), "+f"(d[O+5]), "+f"(d[O+6]), "+f"(d[O+7]), "+f"(d[O+8]), "+f"(d[O+9]), "+f"(d[O+10]), "+f"(d[O+11]), "+f"(d[O+12]), "+f"(d[O+13]), "+f"(d[O+14]), "+f"(d[O+15]), "+f"(d[O+16]), "+f"(d[O+17]), "+f"(d[O+18]), "+f"(d[O+19]), "+f"(d[O+20]), "+f"(d[O+21]), "+f"(d[O+22]), "+f"(d[O+23]), "+f"(d[O+24]), "+f"(d[O+25]), "+f"(d[O+26]), "+f"(d[O+27]), "+f"(d[O+28]), "+f"(d[O+29]), "+f"(d[O+30]), "+f"(d[O+31]), "+f"(d[O+32]), "+f"(d[O+33]), "+f"(d[O+34]), "+f"(d[O+35]), "+f"(d[O+36]), "+f"(d[O+37]), "+f"(d[O+38]), "+f"(d[O+39]), "+f"(d[O+40]), "+f"(d[O+41]), "+f"(d[O+42]), "+f"(d[O+43]), "+f"(d[O+44]), "+f"(d[O+45]), "+f"(d[O+46]), "+f"(d[O+47]), "+f"(d[O+48]), "+f"(d[O+49]), "+f"(d[O+50]), "+f"(d[O+51]), "+f"(d[O+52]), "+f"(d[O+53]), "+f"(d[O+54]), "+f"(d[O+55]), "+f"(d[O+56]), "+f"(d[O+57]), "+f"(d[O+58]), "+f"(d[O+59]), "+f"(d[O+60]), "+f"(d[O+61]), "+f"(d[O+62]), "+f"(d[O+63])
   : "r"(a0), "r"(a1), "r"(a2), "r"(a3), "l"(db), "n"(TB), "r"(sd));
}

#define NEARLY 0
#define XAHEAD 3
#define HM 2
#define SPACE 100
#define WAFTER 7
#define WPACE 100
#define GATE_AT 4
#define TPACE 40
#define PFMODE 0
#define MAPMODE 0
template <int V> struct IC { static constexpr int value = V; };
struct Maps { CUtensorMap x, ft, g64, u64, e, wr, wi, xs, ts, t, g32, u32, d224; };

constexpr int NCTA = 130;
constexpr int U = 16384;
constexpr int TB = 36864;
constexpr int NR = 4;
constexpr int OFF_RING = 8 * U, OFF_Z = 9 * U, OFF_XB = 12 * U, OFF_T = 13 * U, OFF_D = OFF_T;
constexpr int OFF_BAR = 14 * U, OFF_SP = OFF_BAR + 512;
constexpr int SMEM_BYTES = OFF_SP + 1024;
constexpr int B_FX = 0, B_FA = 8, B_FT = 12, B_Z = 16, B_W = 20, B_HX = 21, B_TL = 22, B_HP = 23, B_WR = 26;
constexpr int B_EA = 30, B_ET = 34, B_RDY = 38, B_C1 = 39;
constexpr int B_T = 40, B_XS = 41, NBAR = 43;
__host__ __device__ constexpr int rslot(int n) { return n & 3; }
__host__ __device__ constexpr int rpar(int n) { return (n >> 2) & 1; }

__global__ void __cluster_dims__(2, 1, 1) __launch_bounds__(512, 1)
fused_kernel(const __grid_constant__ Maps maps, const __nv_bfloat16* __restrict__ x, const __nv_bfloat16* __restrict__ w_r,
             const __nv_bfloat16* __restrict__ w_i, const __nv_bfloat16* __restrict__ gate_w, __nv_bfloat16* __restrict__ out) {
  extern __shared__ __align__(1024) uint8_t smem[];
  const uint32_t sb = smem_u32(smem);
  const uint32_t bars = sb + OFF_BAR;
  const int tid = threadIdx.x, lane = tid & 31;
  const int warp = __shfl_sync(0xffffffffu, tid >> 5, 0);
  const bool helper = blockIdx.x >= 128;
  const int cl = (blockIdx.x >> 1) & 63, rank = blockIdx.x & 1;
  const int q4 = cl & 3, rb = cl >> 2;
  const int j = 2 * q4 + rank;
  const int f_full = 448 * q4 + (rank ? 256 : 0);
  const int f_half = 448 * q4 + (rank ? 224 : 192);
  const int kg = 2 * j + (rb >> 3), tn = rb & 7;

  if (tid == 64) { PROF_EV(0); PROF_CK(40); }
  auto ring_part = [&](int p, int n, int slot) {
    const uint32_t fb = bars + 8 * (B_FA + slot), dst = sb + OFF_RING + slot * U + p * 8192;
    const bool table = n == 8 || n == 9 || n >= 30;
    const int q = n < 8 ? n : n - 2;
    if (p == 0) {
      mbar_expect_tx(fb, n < 8 ? U + 8192 : U);
    }
    if (table) { if (p == 0) tma4d(dst, &maps.e, fb, 0, 0, 0, 2 * rb + (n & 1)); }
    else if (n >= 26) tma2d(dst, p ? &maps.u32 : &maps.g32, fb, f_half, 128 * (n - 26));
    else {
      if (n < 8 && p == 1) tma2d(sb + OFF_XB + slot * 8192, &maps.ft, fb, 64 * n, 64 * j);
      tma2d(dst, p ? &maps.u64 : &maps.g64, fb, f_full + 64 * (q >> 3), 64 * (q & 7));
    }
  };
  auto x_load = [&](int q) {
    mbar_expect_tx(bars + 8 * (B_FX + q), U);
    tma3d(sb + q * U, &maps.x, bars + 8 * (B_FX + q), 64 * q, 0, 2 * rb);
  };
  if (warp < 8) {
    asm volatile("barrier.cluster.arrive.relaxed.aligned;" ::: "memory");
    asm volatile("setmaxnreg.inc.sync.aligned.u32 192;");
    if (tid == 0) PROF_EV(33);
    if (!helper) {
      const int wg = warp >> 2, w = warp & 3, g = lane >> 2, q = lane & 3;
      const bool elect = (tid & 127) == 0;
      const uint32_t ep = ld_x1(&g_epoch[blockIdx.x * 8]);
      float cX[32], cA[64], cB[64], ci[64], ct[64];
      const int zero = blockIdx.x >> 16;
      uint32_t h[56], yf[16];
      const uint32_t d0 = (sb & 0x3FFFF) >> 4;
      const uint32_t dK = d0 | (1u << 16), dN = d0 | (512u << 16);
      const uint32_t dX = dK + wg * 512;
      constexpr uint32_t RING = OFF_RING >> 4;
      auto waitA = [&](int n) { mbar_wait(bars + 8 * (B_FA + rslot(n)), rpar(n)); };
      auto freeA = [&](int n) { if (elect) mbar_arrive(bars + 8 * (B_EA + rslot(n))); };
      auto nop = [](int) {};

      asm volatile("bar.sync 0, 384;" ::: "memory");
#pragma unroll 1
      for (int kb = 0; kb < 8; kb++) {
        mbar_wait(bars + 8 * (B_FX + kb), 0); waitA(kb);
        wg_fence();
        const uint64_t dx = d128(dX + kb * 1024), df = d128(dK + (OFF_XB >> 4) + rslot(kb) * 512), db = d128(dN + RING + rslot(kb) * 1024);
        mma_ss64<0, 0, 2>(cX, df, dx, kb);
        mma_ss64<0, 0, 1>(cX, df + 2, dx + 2);
        wg_commit(); wg_wait<1>();
        if (kb) freeA(kb - 1);
        mma_ss64<0, 0, 1>(cX, df + 4, dx + 4);
        mma_ss64<0, 0, 1>(cX, df + 6, dx + 6);
        wg_commit();
        mma_ss128<0, 1, 2>(cA, dx, db, kb);
#pragma unroll
        for (int k = 1; k < 4; k++) mma_ss128<0, 1, 1>(cA, dx + k * 2, db + k * 128);
        wg_commit();
        if (kb == 0 && tid == 0) PROF_EV(1);
      }
      wg_wait<1>();
      fence_regs<0, 32>(cX);
#pragma unroll
      for (int e = 0; e < 16; e++) yf[e] = pack_pin(cX[2 * e], cX[2 * e + 1]);
      if (tid == 0) PROF_EV(2);
      float o0 = 1.0f, o1 = 1.0f;
      auto glu = [&](auto scaled, auto& acc, int half, int ho, int i0, int i1) {
#pragma unroll
        for (int i = i0; i < i1; i++) {
          float a = fmaxf(acc[2 * i], 0.f) * acc[half + 2 * i], b = fmaxf(acc[2 * i + 1], 0.f) * acc[half + 1 + 2 * i];
          if (decltype(scaled)::value) { const float o = (i & 1) ? o1 : o0; a *= o; b *= o; }
          h[ho + i] = pack_pin(a, b);
        }
      };
      {
        waitA(8); waitA(9);
        const uint64_t de = d128(dN + RING + wg * 1024);
        wg_fence();
        mma_rs128<0, 1, 0>(cB, yf[0], yf[1], yf[2], yf[3], de);
        wg_commit();
        wg_wait<1>();
        freeA(7);
        if (elect) mbar_arrive(bars + 8 * B_C1);
        fence_regs<0, 64>(cA);
#pragma unroll
        for (int k = 1; k < 4; k++) { glu(IC<0>(), cA, 32, 0, 4 * k - 4, 4 * k); mma_rs128<0, 1, 1>(cB, yf[4 * k], yf[4 * k + 1], yf[4 * k + 2], yf[4 * k + 3], de + k * 128); }
        wg_commit();
        glu(IC<0>(), cA, 32, 0, 12, 16);
      }
      auto ffn_step = [&](auto first, float (&acc)[64], int n, int kb, auto done, auto work) {
        waitA(n);
        wg_fence();
        const uint64_t dx = d128(dX + kb * 1024), db = d128(dN + RING + rslot(n) * 1024);
        mma_ss128<0, 1, decltype(first)::value>(acc, dx, db, zero);
        wg_commit();
        wg_wait<1>();
        done();
#pragma unroll
        for (int k = 1; k < 4; k++) { work(k - 1); mma_ss128<0, 1, 1>(acc, dx + k * 2, db + k * 128); }
        wg_commit();
        work(3);
      };
      const uint32_t tag = (ep + 1) & 1;
      {
        const int s0 = 2 * rb + wg, kr = 2 * ((s0 & 1) | ((s0 & 4) >> 1));
        const int m = lane >> 3, r = lane & 7;
        const uint32_t a0 = sb + OFF_XB + wg * 8192 + (((w >> 1) * 8 + (m >> 1)) * 2 + (w & 1)) * 256 + (m & 1) * 128 + ((r ^ (kr + (m & 1))) << 4);
        ffn_step(IC<2>(), cA, 10, 0, [&] { freeA(8); freeA(9); fence_regs<0, 64>(cB); }, [&](int i) {
          stsm4t(a0 + i * 1024, pack_bf16(cB[8 * i] - cB[34 + 8 * i], cB[8 * i + 1] - cB[35 + 8 * i]),
                 pack_bf16(cB[32 + 8 * i] + cB[8 * i + 2], cB[33 + 8 * i] + cB[8 * i + 3]),
                 pack_bf16(cB[8 * i + 4] - cB[38 + 8 * i], cB[8 * i + 5] - cB[39 + 8 * i]),
                 pack_bf16(cB[36 + 8 * i] + cB[8 * i + 6], cB[37 + 8 * i] + cB[8 * i + 7]));
        });
        if (j == 0 && w == 0 && g == 0) {
#pragma unroll
          for (int n = 0; n < 8; n++)
#pragma unroll
            for (int ce = 0; ce < 4; ce++)
              *(uint32_t*)(smem + OFF_SP + wg * 512 + ce * 128 + ((n ^ (kr + (ce & 1))) << 4) + 4 * q) =
                  pack_bf16(cB[(ce & 1) * 32 + 4 * n + (ce & 2)], cB[(ce & 1) * 32 + 4 * n + (ce & 2) + 1]);
        }
        ffn_step(IC<1>(), cA, 11, 1, [&] { freeA(10); }, [&](int i) {
          if (i == 1) {
            asm volatile("fence.proxy.async.shared::cta;" ::: "memory");
            __syncwarp();
            if (lane == 0) mbar_arrive(bars + 8 * (B_XS + wg));
            if (tid == 0) PROF_EV(3);
          }
        });
      }
#pragma unroll 1
      for (int kb = 2; kb < 6; kb++) ffn_step(IC<1>(), cA, 10 + kb, kb, [&] { freeA(9 + kb); }, nop);
      const float* gp = g_gate + rb * 128 + wg * 64 + w * 16 + g;
      uint32_t gb0 = ld_x1(gp), gb1 = ld_x1(gp + 8);
#pragma unroll 1
      for (int kb = 6; kb < 8; kb++) ffn_step(IC<1>(), cA, 10 + kb, kb, [&] { freeA(9 + kb); }, nop);
      {
        const uint32_t t0 = (uint32_t)clock();
        while (__any_sync(0xffffffffu, ((gb0 ^ tag) | (gb1 ^ tag)) & 1)) { gb0 = ld_x1(gp); gb1 = ld_x1(gp + 8); spin_guard(t0); }
      }
      const float g0 = __uint_as_float(gb0 & ~1u), g1 = __uint_as_float(gb1 & ~1u);
      o0 = 1.0f - g0; o1 = 1.0f - g1;
      ffn_step(IC<2>(), cB, 18, 0, [&] { freeA(17); fence_regs<0, 64>(cA); }, [&](int i) { glu(IC<1>(), cA, 32, 16, 2 * i, 2 * i + 2); });
      if (tid == 0) PROF_EV(4);
      ffn_step(IC<1>(), cB, 19, 1, [&] { freeA(18); }, [&](int i) { glu(IC<1>(), cA, 32, 16, 8 + 2 * i, 10 + 2 * i); });
      ffn_step(IC<1>(), cB, 20, 2, [&] { freeA(19); }, [&](int i) {
#pragma unroll
        for (int e = 4 * i; e < 4 * i + 4; e++) { const float o = (e & 1) ? o1 : o0; h[e] = pack_pin(bf_lo(h[e]) * o, bf_hi(h[e]) * o); }
      });
#pragma unroll 1
      for (int kb = 3; kb < 8; kb++) ffn_step(IC<1>(), cB, 18 + kb, kb, [&] { freeA(17 + kb); }, nop);
      if (tid == 0) PROF_EV(5);
      auto m_step = [&](auto first, int i, auto done, auto work) {
        waitA(26 + i);
        wg_fence();
        const uint64_t dx = d128(dX + i * 2048), dm = d64(dN + RING + rslot(26 + i) * 1024);
        mma_ss64<0, 1, decltype(first)::value>(ct, dx, dm);
        mma_ss64<0, 1, 1>(ct, dx + 2, dm + 64);
        wg_commit();
        wg_wait<1>();
        done();
#pragma unroll
        for (int k = 2; k < 8; k++) { if (k & 1) work(k / 2 - 1); mma_ss64<0, 1, 1>(ct, dx + ((k >> 2) * 1024 + (k & 3) * 2), dm + k * 64); }
        wg_commit();
        work(3);
      };
      auto freeT = [&](int t) { if (elect) mbar_arrive(bars + 8 * (B_ET + t)); };
      m_step(IC<0>(), 0, [&] { freeA(25); fence_regs<0, 64>(cB); }, [&](int i) { glu(IC<1>(), cB, 32, 32, 2 * i, 2 * i + 2); });
      m_step(IC<1>(), 1, [&] { freeA(26); freeT(0); }, [&](int i) { glu(IC<1>(), cB, 32, 32, 8 + 2 * i, 10 + 2 * i); });
      m_step(IC<1>(), 2, [&] { freeA(27); freeT(1); }, nop);
      m_step(IC<1>(), 3, [&] { freeT(2); }, nop);
      if (wg) waitA(31); else waitA(30);
      if (tid == 0) PROF_EV(6);
      mbar_wait(bars + 8 * (j == 0 ? B_T : B_TL), 0);
      if (tid == 0) PROF_EV(7);
      wg_fence();
      {
        const uint64_t dt = d128(dN + (OFF_T >> 4) + wg * 512), de = d128(dK + RING + (2 + wg) * 1024);
        mma_ss64<0, 1, 0>(ci, de, dt);
        mma_ss64<32, 1, 0>(ci, de + 512, dt);
        wg_commit();
        wg_wait<1>();
        freeT(3);
        fence_regs<0, 32>(ct);
#pragma unroll
        for (int k = 1; k < 4; k++) {
          mma_ss64<0, 1, 1>(ci, de + k * 2, dt + k * 128);
          mma_ss64<32, 1, 1>(ci, de + (512 + k * 2), dt + k * 128);
          if (k < 3) glu(IC<1>(), ct, 16, 48, 4 * k - 4, 4 * k);
        }
        wg_commit();
      }

      auto head = [&](auto off, int t, auto first) {
        constexpr int O = decltype(off)::value;
        mbar_wait(bars + 8 * (B_FT + (t & 3)), t >> 2);
        const uint64_t db = d128(dN + (t & 3) * (TB >> 4) + rank * 256);
        wg_fence();
        mma_rs64<O, 1, decltype(first)::value>(ct, h[0], h[1], h[2], h[3], db, zero);
#pragma unroll
        for (int k = 1; k < 6; k++) mma_rs64<O, 1, 1>(ct, h[4 * k], h[4 * k + 1], h[4 * k + 2], h[4 * k + 3], db + k * 128);
        wg_commit();
        wg_wait<1>();
      };
      auto rest = [&](auto off, int t) {
        constexpr int O = decltype(off)::value;
        const uint64_t db = d128(dN + (t & 3) * (TB >> 4)), dw = db + rank * 256, dm = db + (rank ? 0 : 1536);
        wg_fence();
#pragma unroll
        for (int k = 6; k < 12; k++) mma_rs64<O, 1, 1>(ct, h[4 * k], h[4 * k + 1], h[4 * k + 2], h[4 * k + 3], dw + k * 128);
#pragma unroll
        for (int k = 0; k < 2; k++) mma_rs64<O, 1, 1>(ct, h[48 + 4 * k], h[49 + 4 * k], h[50 + 4 * k], h[51 + 4 * k], dm + k * 128);
#pragma unroll
        for (int k = 0; k < 4; k++) mma_rs64<O, 1, 1>(ct, yf[4 * k], yf[4 * k + 1], yf[4 * k + 2], yf[4 * k + 3], db + (14 + k) * 128);
        wg_commit();
      };
      const uint32_t peerZ = mapa(sb + OFF_Z + tid * 16, rank ^ 1), peerB = mapa(bars + 8 * B_Z, rank ^ 1);
      auto send_peer = [&](auto off, int z) {
        constexpr int O = decltype(off)::value;
        fence_regs<O, 32>(ct);
#pragma unroll
        for (int i = 0; i < 4; i++)
          asm volatile("st.async.weak.shared::cluster.mbarrier::complete_tx::bytes.v4.b32 [%0], {%1,%2,%3,%4}, [%5];" ::"r"(peerZ + z * U + i * 4096),
                       "r"(pack_bf16(ct[O + 8 * i], ct[O + 8 * i + 1])), "r"(pack_bf16(ct[O + 8 * i + 2], ct[O + 8 * i + 3])),
                       "r"(pack_bf16(ct[O + 8 * i + 4], ct[O + 8 * i + 5])), "r"(pack_bf16(ct[O + 8 * i + 6], ct[O + 8 * i + 7])), "r"(peerB + 8 * z) : "memory");
      };
      auto send_grid = [&](auto off, int z) {
        constexpr int O = decltype(off)::value;
        fence_regs<O, 32>(ct);
        mbar_wait(bars + 8 * (B_Z + z), 0);
        uint4* dst = g_part + (size_t)((rb * 8 + 2 * ((q4 + z + 1) & 3) + rank) * 3 + z) * 1024 + tid;
#pragma unroll
        for (int i = 0; i < 4; i++) {
          const uint4 p = *(const uint4*)(smem + OFF_Z + z * U + i * 4096 + tid * 16);
          st_x4(dst + i * 256, (pack_bf16(ct[O + 8 * i] + bf_lo(p.x), ct[O + 8 * i + 1] + bf_hi(p.x)) & ~1u) | tag,
                pack_bf16(ct[O + 8 * i + 2] + bf_lo(p.y), ct[O + 8 * i + 3] + bf_hi(p.y)),
                pack_bf16(ct[O + 8 * i + 4] + bf_lo(p.z), ct[O + 8 * i + 5] + bf_hi(p.z)),
                pack_bf16(ct[O + 8 * i + 6] + bf_lo(p.w), ct[O + 8 * i + 7] + bf_hi(p.w)));
        }
        __syncwarp();
        if (lane == 0) hint_add(&g_cntP[32 * (rb * 8 + 2 * ((q4 + z + 1) & 3) + rank) + z]);
      };
      asm volatile("barrier.cluster.wait.aligned;" ::: "memory");
      head(IC<0>(), 0, IC<2>());
      if (elect) asm volatile("mbarrier.arrive.shared::cluster.b64 _, [%0];" ::"r"(mapa(bars + 8 * B_RDY, rank ^ 1)) : "memory");
      fence_regs<0, 64>(ci);
#pragma unroll
      for (int i = 0; i < 16; i++) {
        const float gg = ((i & 1) ? g1 : g0) * (2.0f / (2048.0f * 512.0f));
        if (i & 2) yf[i] = pack_pin((ci[2 * i] - ci[28 + 2 * i]) * gg, (ci[2 * i + 1] - ci[29 + 2 * i]) * gg);
        else yf[i] = pack_pin((ci[2 * i] + ci[36 + 2 * i]) * gg, (ci[2 * i + 1] + ci[37 + 2 * i]) * gg);
      }
      rest(IC<0>(), 0);
      if (tid == 0) PROF_EV(8);
      head(IC<32>(), 1, IC<HM>()); freeT(0); mbar_wait(bars + 8 * B_RDY, 0); send_peer(IC<0>(), 0); rest(IC<32>(), 1);
      head(IC<0>(), 2, IC<HM>()); freeT(1); send_peer(IC<32>(), 1); rest(IC<0>(), 2);
      head(IC<32>(), 3, IC<HM>()); freeT(2); send_peer(IC<0>(), 2); rest(IC<32>(), 3);
      head(IC<0>(), 4, IC<HM>()); freeT(3); send_grid(IC<32>(), 0); rest(IC<0>(), 4);
      head(IC<32>(), 5, IC<HM>()); send_grid(IC<0>(), 1); rest(IC<32>(), 5);
      head(IC<0>(), 6, IC<HM>()); send_grid(IC<32>(), 2); rest(IC<0>(), 6);
      head(IC<32>(), 7, IC<HM>()); send_peer(IC<0>(), 3);
      {
        const uint4* src = g_part + (size_t)(rb * 8 + j) * 3 * 1024 + tid;
        uint4 pv[12];
        mbar_wait(bars + 8 * (B_HP + 1), 0);
#pragma unroll
        for (int i = 0; i < 8; i++) pv[i] = ld_x4(src + i * 256);
        rest(IC<32>(), 7);
        if (tid == 0) PROF_EV(9);
        mbar_wait(bars + 8 * (B_HP + 2), 0);
        if (tid == 0) PROF_EV(24);
#pragma unroll
        for (int i = 8; i < 12; i++) pv[i] = ld_x4(src + i * 256);
        const uint32_t t0 = (uint32_t)clock();
        for (;;) {
          uint32_t bad = 0;
#pragma unroll
          for (int i = 0; i < 12; i++) bad |= pv[i].x ^ tag;
          if (!__any_sync(0xffffffffu, bad & 1)) break;
#pragma unroll
          for (int i = 0; i < 12; i++) pv[i] = ld_x4(src + i * 256);
          spin_guard(t0);
        }
        if (tid == 0) PROF_EV(14);
        float sum[32];
#pragma unroll
        for (int i = 0; i < 4; i++) {
          const uint32_t a[4] = {pv[i].x & ~1u, pv[i].y, pv[i].z, pv[i].w}, b[4] = {pv[4 + i].x & ~1u, pv[4 + i].y, pv[4 + i].z, pv[4 + i].w},
                         c[4] = {pv[8 + i].x & ~1u, pv[8 + i].y, pv[8 + i].z, pv[8 + i].w};
#pragma unroll
          for (int e = 0; e < 4; e++) {
            sum[8 * i + 2 * e] = bf_lo(a[e]) + bf_lo(b[e]) + bf_lo(c[e]);
            sum[8 * i + 2 * e + 1] = bf_hi(a[e]) + bf_hi(b[e]) + bf_hi(c[e]);
          }
        }
        mbar_wait(bars + 8 * (B_Z + 3), 0);
#pragma unroll
        for (int i = 0; i < 4; i++) {
          const uint4 p = *(const uint4*)(smem + OFF_Z + 3 * U + i * 4096 + tid * 16);
          const uint32_t a[4] = {p.x, p.y, p.z, p.w};
#pragma unroll
          for (int e = 0; e < 4; e++) { sum[8 * i + 2 * e] += bf_lo(a[e]); sum[8 * i + 2 * e + 1] += bf_hi(a[e]); }
        }
        wg_wait<0>();
        fence_regs<32, 32>(ct);
#pragma unroll
        for (int i = 0; i < 32; i++) sum[i] += ct[32 + i];
        const uint32_t stg = sb + OFF_T + warp * 2048;
        const int mr = (lane & 7) + ((lane >> 3) & 1) * 8, mc = lane >> 4;
#pragma unroll
        for (int i = 0; i < 4; i++) {
          const uint32_t a = stg + mr * 128 + (((2 * i + mc) ^ (mr & 7)) << 4);
          asm volatile("stmatrix.sync.aligned.m8n8.x4.shared.b16 [%0], {%1,%2,%3,%4};" ::"r"(a), "r"(pack_bf16(sum[8 * i], sum[8 * i + 1])),
                       "r"(pack_bf16(sum[8 * i + 2], sum[8 * i + 3])), "r"(pack_bf16(sum[8 * i + 4], sum[8 * i + 5])),
                       "r"(pack_bf16(sum[8 * i + 6], sum[8 * i + 7])) : "memory");
        }
        __syncwarp();
#pragma unroll
        for (int i = 0; i < 4; i++) {
          const int r = 4 * i + (lane >> 3), c = lane & 7;
          const uint4 v = *(const uint4*)(smem + OFF_T + warp * 2048 + r * 128 + ((c ^ (r & 7)) << 4));
          *(uint4*)(out + (size_t)(2 * rb + wg + 32 * (16 * w + r)) * 512 + 64 * j + 8 * c) = v;
        }
      }
      if (tid == 0) { g_epoch[blockIdx.x * 8] = ep + 1; PROF_EV(15); PROF_CK(41); }
    }
  } else if (warp < 12) {
    asm volatile("setmaxnreg.dec.sync.aligned.u32 104;");
    asm volatile("barrier.cluster.arrive.relaxed.aligned;" ::: "memory");
    const int t = tid - 256, w = warp - 8;
    const uint32_t ep = ld_x1(&g_epoch[blockIdx.x * 8]);
    const uint32_t tag = (ep + 1) & 1;
    auto gate_rows = [&] {
      uint4 xv[8], gv[2];
#pragma unroll
      for (int i = 0; i < 4; i++) {
        const int r = 16 * j + 4 * w + i;
        const uint4* p = (const uint4*)(x + (size_t)(2 * rb + (r >> 6) + 32 * (r & 63)) * 512) + lane;
        xv[2 * i] = __ldg(p); xv[2 * i + 1] = __ldg(p + 32);
      }
      gv[0] = __ldg((const uint4*)gate_w + lane); gv[1] = __ldg((const uint4*)gate_w + lane + 32);
      {
        float z[4];
#pragma unroll
        for (int i = 0; i < 4; i++) {
          float a = 0.f;
#pragma unroll
          for (int hh = 0; hh < 2; hh++) {
            const uint4 u = xv[2 * i + hh], v = gv[hh];
            a = fmaf(bf_lo(u.x), bf_lo(v.x), a); a = fmaf(bf_hi(u.x), bf_hi(v.x), a);
            a = fmaf(bf_lo(u.y), bf_lo(v.y), a); a = fmaf(bf_hi(u.y), bf_hi(v.y), a);
            a = fmaf(bf_lo(u.z), bf_lo(v.z), a); a = fmaf(bf_hi(u.z), bf_hi(v.z), a);
            a = fmaf(bf_lo(u.w), bf_lo(v.w), a); a = fmaf(bf_hi(u.w), bf_hi(v.w), a);
          }
#pragma unroll
          for (int o = 16; o; o >>= 1) a += __shfl_xor_sync(0xffffffffu, a, o);
          z[i] = a;
        }
        if (lane < 4) {
          const float zz = lane == 0 ? z[0] : lane == 1 ? z[1] : lane == 2 ? z[2] : z[3];
          asm volatile("st.relaxed.gpu.global.f32 [%0], %1;" ::"l"(g_gate + rb * 128 + 16 * j + 4 * w + lane), "f"(tagf(1.0f / (1.0f + __expf(-zz)), tag)) : "memory");
        }
        if (t == 0) PROF_EV(18);
      }
      if (w == 0) {
        const int c = lane >> 4, jj = 16 * blockIdx.x + (lane & 15), jm = (2048 - jj) & 2047;
        const unsigned short* pr = (const unsigned short*)w_r + 256 * c;
        const unsigned short* pi = (const unsigned short*)w_i + 256 * c;
        const float wr = 0.25f * (bf_lo(__ldg(pr + jj * 257)) + bf_lo(__ldg(pr + jm * 257)));
        const float wi = 0.25f * (bf_lo(__ldg(pi + jj * 257)) - bf_lo(__ldg(pi + jm * 257)));
        st_u2(g_Wh + c * 2048 + jj, c ? pack_bf16(-wi, wr) : pack_bf16(wr, wi), tag);
        __syncwarp();
        if (lane == 0) hint_add(&g_cntW[0]);
      }
    };
    {
      const int g = lane >> 2, q = lane & 3;
      uint32_t wf[32];
      if (!helper) {
        asm volatile("bar.sync 4, 256;" ::: "memory");
        mbar_wait(bars + 8 * (B_FX + GATE_AT), 0);
        gate_rows();
        const uint32_t wa = sb + OFF_T + w * (3072 + 4) + q * 48 + g * 2;
        mbar_wait(bars + 8 * B_C1, 0);
        if (t == 0) PROF_EV(32);
        __nanosleep(WPACE * w);
#pragma unroll
        for (int ri = 0; ri < 2; ri++) {
          if (lane == 0) {
            mbar_expect_tx(bars + 8 * (B_WR + w), 3072);
            tma4d(sb + OFF_T + w * 3072, ri ? &maps.wi : &maps.wr, bars + 8 * (B_WR + w), 16 * kg, 0, 2 * w, tn);
          }
          mbar_wait(bars + 8 * (B_WR + w), ri);
#pragma unroll
          for (int n2 = 0; n2 < 4; n2++) {
            uint32_t v[8];
#pragma unroll
            for (int i = 0; i < 8; i++)
              asm volatile("ld.shared.u16 %0, [%1];" : "=r"(v[i]) : "r"(wa + (2 * n2 + ((i >> 1) & 1)) * 192 + (i & 1) * (1536 + 2) + (i >> 2) * 16) : "memory");
#pragma unroll
            for (int i = 0; i < 8; i++) {
              uint32_t& d = wf[(i >> 2) * 16 + 4 * n2 + (i & 3)];
              d = ri ? d | (v[i] << 16) : v[i];
              asm volatile("" : "+r"(d)::"memory");
            }
          }
          __syncwarp();
        }
        asm volatile("bar.sync 1, 128;" ::: "memory");
        if (t == 0) PROF_EV(11);
      } else {
        asm volatile("bar.sync 4, 256;" ::: "memory");
        hint_wait(&g_cntW[0], (ep + 1) * 128u);
        const uint32_t t0 = (uint32_t)clock();
#pragma unroll 1
        for (;;) {
          uint32_t bad = 0;
#pragma unroll
          for (int i = 0; i < 32; i++) {
            const float2 v = ld_x2((const float2*)g_Wh + (i >> 4) * 2048 + 16 * w + g + 8 * (i & 1) + 64 * q + ((i >> 1) & 7) * 256);
            wf[i] = __float_as_uint(v.x); bad |= __float_as_uint(v.y) ^ tag;
          }
          if (!__any_sync(0xffffffffu, bad & 1)) break;
          spin_guard(t0);
        }
        if (t == 0) PROF_EV(11);
      }
      if (t == 0) { mbar_expect_tx(bars + 8 * B_W, 8192); bulk_load(sb + OFF_D, g_DT.v, 8192, bars + 8 * B_W); }
      mbar_wait(bars + 8 * B_W, 0);
      mbar_wait(bars + 8 * B_HX, 0);
      if (t == 0) PROF_EV(12);
      const uint32_t dd = (sb & 0x3FFFF) >> 4;
      const uint64_t dF = d128((dd + (OFF_D >> 4)) | (512u << 16)), dI = d128((dd + (OFF_D >> 4)) | (1u << 16)), dA = d128((dd + (OFF_XB >> 4)) | (512u << 16));
      float az[32];
      const int zero = blockIdx.x >> 16;
      uint32_t pf[32];
#pragma unroll
      for (int mt = 0; mt < 2; mt++) {
        wg_fence();
        if (mt == 0) mma_ss64<0, 3, 0>(az, dA, dF);
        else mma_ss64<0, 3, 2>(az, dA + 512, dF, zero);
#pragma unroll
        for (int k = 1; k < 4; k++) mma_ss64<0, 3, 1>(az, dA + (mt * 512 + k * 128), dF + k * 128);
        wg_commit();
        wg_wait<0>();
        fence_regs<0, 32>(az);
#pragma unroll
        for (int i = 0; i < 16; i++) {
          const float wr = bf_lo(wf[16 * mt + i]), wi = bf_hi(wf[16 * mt + i]);
          pf[16 * mt + i] = pack_pin(fmaf(az[2 * i], wr, -az[2 * i + 1] * wi), fmaf(az[2 * i], wi, az[2 * i + 1] * wr));
        }
      }
      if (t == 0) PROF_EV(16);
#pragma unroll
      for (int mt = 0; mt < 2; mt++) {
        wg_fence();
        mma_rs64<0, 0, 2>(az, pf[16 * mt], pf[16 * mt + 1], pf[16 * mt + 2], pf[16 * mt + 3], dI, mt ? (int)helper : zero);
#pragma unroll
        for (int k = 1; k < 4; k++) mma_rs64<0, 0, 1>(az, pf[16 * mt + 4 * k], pf[16 * mt + 4 * k + 1], pf[16 * mt + 4 * k + 2], pf[16 * mt + 4 * k + 3], dI + k * 2);
        wg_commit();
        wg_wait<0>();
        fence_regs<0, 32>(az);
        if (!helper) {
          const int m = lane >> 3, r = lane & 7;
          const int sl = 2 * (m >> 1) + ((r >> 1) & 1) + 4 * (r >> 2);
          const uint32_t a0 = sb + OFF_XB + (2 * w + (m & 1)) * 2048 + sl * 64 + (((mt * 2 + (r & 1)) ^ (sl >> 1)) << 4);
#pragma unroll
          for (int i = 0; i < 4; i++)
            stsm4t(a0 + i * 512, pack_bf16(az[8 * i], az[8 * i + 1]), pack_bf16(az[8 * i + 2], az[8 * i + 3]), pack_bf16(az[8 * i + 4], az[8 * i + 5]),
                   pack_bf16(az[8 * i + 6], az[8 * i + 7]));
        }
      }
      if (helper) {
#pragma unroll
        for (int i = 0; i < 16; i++) {
          const int n = i >> 1, s0 = 8 * (n >> 1) + 2 * (n & 1) + (q & 1) + 4 * (q >> 1);
          if ((n & 1) == (int)(blockIdx.x & 1)) st_u2(g_Ts + s0 * 64 + 16 * w + g + 8 * (i & 1), pack_bf16(az[2 * i], az[2 * i + 1]), tag);
        }
        __syncwarp();
        if (lane == 0) hint_add(&g_cntH[0]);
        if (t == 0) { g_epoch[blockIdx.x * 8] = ep + 1; PROF_EV(13); }
      } else {
        asm volatile("fence.proxy.async.shared::cta;" ::: "memory");
        __syncwarp();
        if (lane == 0) {
          if (t == 0) PROF_EV(17);
          if (SPACE) __nanosleep(SPACE * w);
          asm volatile("cp.async.bulk.tensor.3d.global.shared::cta.bulk_group [%0, {%2, %3, %4}], [%1];" ::"l"(&maps.ts), "r"(sb + OFF_XB + w * 4096),
                       "r"(32 * kg), "r"(0), "r"(8 * tn + 2 * w) : "memory");
          bulk_done_signal(&g_cntT[32 * j]);
          if (t == 96) PROF_EV(13);
        }
        __syncwarp();
        if (j == 0) {
          hint_wait(&g_cntH[0], (ep + 1) * 8u);
          const uint32_t t0 = (uint32_t)clock();
          float2 v;
          do { v = ld_x2((const float2*)g_Ts + 2 * rb * 64 + t); spin_guard(t0); } while (__any_sync(0xffffffffu, (__float_as_uint(v.y) ^ tag) & 1));
          mbar_wait(bars + 8 * B_TL, 0);
          const uint32_t u = __float_as_uint(v.x);
          *(uint16_t*)(smem + OFF_T + t * 128 + ((t & 7) << 4)) = (uint16_t)u;
          *(uint16_t*)(smem + OFF_T + t * 128 + (((t & 7) ^ 1) << 4)) = (uint16_t)(u >> 16);
          asm volatile("fence.proxy.async.shared::cta;" ::: "memory");
          __syncwarp();
          if (lane == 0) mbar_arrive(bars + 8 * B_T);
        }
      }
    }
  } else {
    asm volatile("setmaxnreg.dec.sync.aligned.u32 24;");
    if (warp < 14) {
      if (lane == 0) {
#pragma unroll
        for (int i = 0; i < 6; i++) mbar_init(bars + 8 * (2 * i + warp - 12), 1);
        asm volatile("fence.proxy.async.shared::cta;" ::: "memory");
      }
      asm volatile("bar.sync 2, 64;" ::: "memory");
      asm volatile("bar.arrive 0, 384;" ::: "memory");
      asm volatile("bar.arrive 4, 256;" ::: "memory");
      if (lane == 0) {
        if (!helper) {
#pragma unroll 1
          for (int n = 0; n < NR; n++) { if (warp == 12) x_load(n); ring_part(warp - 12, n, n); }
        }
      }
    } else {
      if (lane != 0) {
      } else if (warp == 15) {
#pragma unroll
        for (int i = B_FT; i < NBAR; i++) mbar_init(bars + 8 * i, i < B_EA ? 1 : i < B_T ? 2 : 4);
#pragma unroll
        for (int i = 0; i < 4; i++) mbar_expect_tx(bars + 8 * (B_Z + i), U);
        asm volatile("fence.mbarrier_init.release.cluster;" ::: "memory");
        asm volatile("fence.proxy.async.shared::cta;" ::: "memory");
      } else {
#pragma unroll
        for (int i = 1; i < 4; i++) asm volatile("prefetch.tensormap [%0];" ::"l"((const char*)&maps + i * 128) : "memory");
      }
      __syncwarp();
      asm volatile("bar.arrive 0, 384;" ::: "memory");
      asm volatile("bar.arrive 4, 256;" ::: "memory");
    }
    __syncwarp();
    asm volatile("barrier.cluster.arrive.relaxed.aligned;" ::: "memory");
    asm volatile("bar.sync 3, 128;" ::: "memory");
    if (lane == 0 && (!helper || warp == 15)) {
      if (warp < 14) {
        if (warp == 12) x_load(NR);
        int slot = 0, par = 0;
#pragma unroll 1
        for (int n = NR; n < 32; n++) {
          mbar_wait(bars + 8 * (B_EA + slot), par);
          ring_part(warp - 12, n, slot);
          if (warp == 12 && n < 7) x_load(n + 1);
          if (++slot == NR) { slot = 0; par ^= 1; }
        }
      } else if (warp == 15) {
        const unsigned ep1 = ld_x1(&g_epoch[blockIdx.x * 8]) + 1;
        flag_wait(&g_cntX[helper ? 0 : 32 * j], ep1 * 16u);
        PROF_EV(22);
        mbar_expect_tx(bars + 8 * B_HX, U);
        bulk_load(sb + OFF_XB, g_X + (size_t)(helper ? 128 : kg * 8 + tn) * 8192, U, bars + 8 * B_HX);
        if (!helper) {
          flag_wait(&g_cntT[32 * j], ep1 * 64u);
          PROF_EV(23);
          mbar_expect_tx(bars + 8 * B_TL, U);
          tma3d(sb + OFF_T, &maps.t, bars + 8 * B_TL, 64 * j, 0, 2 * rb);
#pragma unroll 1
          for (int i = 0; i < 3; i++) { hint_wait(&g_cntP[32 * (rb * 8 + j) + i], ep1 * 8u); mbar_arrive(bars + 8 * (B_HP + i)); }
        }
      } else {
#pragma unroll 1
        for (int h2 = 0; h2 < 2; h2++) {
          const int s0 = 2 * rb + h2, sg = (s0 & ~6) | ((s0 & 2) << 1) | ((s0 & 4) >> 1);
          mbar_wait(bars + 8 * (B_XS + h2), 0);
#pragma unroll 1
          for (int c = 0; c < 2; c++) {
            asm volatile("cp.async.bulk.tensor.4d.global.shared::cta.bulk_group [%0, {%2, %3, %4, %5}], [%1];" ::"l"(&maps.xs),
                         "r"(sb + OFF_XB + h2 * 8192 + c * 4096), "r"(0), "r"(sg), "r"(0), "r"(16 * j + 8 * c) : "memory");
            if (j == 0)
              asm volatile("cp.async.bulk.global.shared::cta.bulk_group [%0], [%1], 256;" ::"l"(g_X + 128 * 8192 + c * 4096 + sg * 128),
                           "r"(sb + OFF_SP + h2 * 512 + c * 256) : "memory");
            if (SPACE && h2 + c < 2) __nanosleep(SPACE);
          }
        }
        bulk_done_signal(&g_cntX[32 * j]);
        PROF_EV(20);
#pragma unroll 1
        for (int t = 0; t < 8; t++) {
          const int i = t < 3 ? t + 1 : t < 6 ? t - 2 : 0;
          const int col = 64 * (2 * ((q4 + i) & 3) + ((t < 3 || t == 6) ? 1 - rank : rank));
          const uint32_t fb = bars + 8 * (B_FT + (t & 3)), dst = sb + (t & 3) * TB;
          mbar_wait(bars + 8 * (B_ET + (t == 2 ? 3 : t & 3)), t >> 2);
          mbar_expect_tx(fb, TB);
          tma2d(dst, &maps.d224, fb, col, 224 * j);
          if (t < 2) mbar_wait(bars + 8 * (B_ET + t + 1), 0);
          tma2d(dst + 28672, &maps.ft, fb, col, 64 * j);
        }
      }
    }
  }
}

typedef CUresult (*EncodeFn)(CUtensorMap*, CUtensorMapDataType, cuuint32_t, void*, const cuuint64_t*, const cuuint64_t*, const cuuint32_t*,
                             const cuuint32_t*, CUtensorMapInterleave, CUtensorMapSwizzle, CUtensorMapL2promotion, CUtensorMapFloatOOBfill);

static void encode(EncodeFn f, CUtensorMap* m, const void* base, int rank, const cuuint64_t* dims, const cuuint64_t* strides, const cuuint32_t* box,
                   CUtensorMapSwizzle sw) {
  cuuint32_t es[5] = {1, 1, 1, 1, 1};
  f(m, CU_TENSOR_MAP_DATA_TYPE_BFLOAT16, rank, (void*)base, dims, strides, box, es, CU_TENSOR_MAP_INTERLEAVE_NONE, sw,
    CU_TENSOR_MAP_L2_PROMOTION_L2_128B, CU_TENSOR_MAP_FLOAT_OOB_FILL_NONE);
}

extern "C" void kernel_launch(void* const* d_in, const int* in_sizes, int n_in, void* d_out, int out_size) {
  (void)in_sizes; (void)n_in; (void)out_size;
  const __nv_bfloat16* x = (const __nv_bfloat16*)d_in[0];
  const __nv_bfloat16* w_r = (const __nv_bfloat16*)d_in[1];
  const __nv_bfloat16* w_i = (const __nv_bfloat16*)d_in[2];
  const __nv_bfloat16* Wg = (const __nv_bfloat16*)d_in[4];
  const __nv_bfloat16* Wu = (const __nv_bfloat16*)d_in[5];
  const __nv_bfloat16* Wd = (const __nv_bfloat16*)d_in[6];
  const __nv_bfloat16* gw = (const __nv_bfloat16*)d_in[7];

  void* fp = nullptr; cudaDriverEntryPointQueryResult qr;
  cudaGetDriverEntryPoint("cuTensorMapEncodeTiled", &fp, cudaEnableDefault, &qr);
  EncodeFn enc = (EncodeFn)fp;
  void *pFT, *pET, *pX, *pT;
  cudaGetSymbolAddress(&pX, g_X); cudaGetSymbolAddress(&pT, g_T);
  cudaGetSymbolAddress(&pFT, g_FT); cudaGetSymbolAddress(&pET, g_ET);

  Maps mp;
  const CUtensorMapSwizzle S128 = CU_TENSOR_MAP_SWIZZLE_128B, S64 = CU_TENSOR_MAP_SWIZZLE_64B;
  { cuuint64_t d[3] = {512, 64, 32}, s[2] = {32768, 1024}; cuuint32_t b[3] = {64, 64, 2}; encode(enc, &mp.x, x, 3, d, s, b, S128); }
  { cuuint64_t d[2] = {512, 512}, s[1] = {1024}; cuuint32_t b[2] = {64, 64}; encode(enc, &mp.ft, pFT, 2, d, s, b, S128); }
  { cuuint64_t d[4] = {128, 32, 2, 129}, s[3] = {256, 8192, 16384}; cuuint32_t b[4] = {128, 1, 2, 8}; encode(enc, &mp.xs, pX, 4, d, s, b, CU_TENSOR_MAP_SWIZZLE_NONE); }
  { cuuint64_t d[3] = {512, 32, 64}, s[2] = {65536, 1024}; cuuint32_t b[3] = {32, 32, 2}; encode(enc, &mp.ts, pT, 3, d, s, b, S64); }
  { cuuint64_t d[3] = {512, 64, 32}, s[2] = {1024, 65536}; cuuint32_t b[3] = {64, 64, 2}; encode(enc, &mp.t, pT, 3, d, s, b, S128); }
  { cuuint64_t d[4] = {64, 64, 2, 32}, s[3] = {8192, 128, 256}; cuuint32_t b[4] = {64, 64, 2, 1}; encode(enc, &mp.e, pET, 4, d, s, b, S128); }
  { cuuint64_t d[2] = {1792, 512}, s[1] = {3584}; cuuint32_t b[2] = {64, 64}, b2[2] = {32, 128};
    encode(enc, &mp.g64, Wg, 2, d, s, b, S128); encode(enc, &mp.u64, Wu, 2, d, s, b, S128);
    encode(enc, &mp.g32, Wg, 2, d, s, b2, S64); encode(enc, &mp.u32, Wu, 2, d, s, b2, S64); }
  { cuuint64_t d[2] = {512, 1792}, s[1] = {1024}; cuuint32_t b[2] = {64, 224}; encode(enc, &mp.d224, Wd, 2, d, s, b, S128); }
  { cuuint64_t d[4] = {264, 32, 8, 8}, s[3] = {32896, 512, 4112}; cuuint32_t b[4] = {24, 32, 2, 1};
    encode(enc, &mp.wr, w_r, 4, d, s, b, CU_TENSOR_MAP_SWIZZLE_NONE); encode(enc, &mp.wi, w_i, 4, d, s, b, CU_TENSOR_MAP_SWIZZLE_NONE); }

  cudaFuncSetAttribute(fused_kernel, cudaFuncAttributeMaxDynamicSharedMemorySize, SMEM_BYTES);
  fused_kernel<<<NCTA, 512, SMEM_BYTES>>>(mp, x, w_r, w_i, gw, (__nv_bfloat16*)d_out);
}
```

```cpp
#include <cuda_runtime.h>
#include <cuda_bf16.h>
#include <cuda.h>
#include <stdint.h>

namespace tbl {
constexpr double PI = 3.14159265358979323846264338327950288;
constexpr double sin_s(double x) { double t = x, s = x; for (int n = 1; n < 12; n++) { t *= -x * x / ((2 * n) * (2 * n + 1)); s += t; } return s; }
constexpr double cos_s(double x) { double t = 1, s = 1; for (int n = 1; n < 12; n++) { t *= -x * x / ((2 * n - 1) * (2 * n)); s += t; } return s; }
constexpr double cos2048(int m) {
  m &= 2047; if (m > 1024) m = 2048 - m;
  bool neg = false; if (m > 512) { m = 1024 - m; neg = true; }
  double v = (m <= 256) ? cos_s(2 * PI * m / 2048) : sin_s(2 * PI * (512 - m) / 2048);
  return neg ? -v : v;
}
constexpr uint16_t to_bf16(double v) {
  if (v == 0) return 0;
  uint16_t s = 0; if (v < 0) { s = 0x8000; v = -v; }
  int e = 0; while (v >= 2) { v /= 2; e++; } while (v < 1) { v *= 2; e--; }
  double m = (v - 1) * 128; int mi = (int)m; double fr = m - mi;
  if (fr > 0.5 || (fr == 0.5 && (mi & 1))) mi++;
  if (mi == 128) { mi = 0; e++; }
  return (uint16_t)(s | ((e + 127) << 7) | mi);
}
struct CosT { uint16_t v[2048]; constexpr CosT() : v() { for (int i = 0; i < 2048; i++) v[i] = to_bf16(cos2048(i)); } };
struct alignas(1024) FT {
  uint16_t v[512 * 512];
  constexpr FT() : v() {
    CosT c;
    for (int r = 0; r < 512; r++) {
      int k = (r >> 4) * 8 + (r & 7), e = (r >> 3) & 1;
      int mul = 4 * k, add = e ? 512 : 0;
      if (k == 0 && e == 1) { mul = 1024; add = 0; }
      for (int d = 0; d < 512; d++) v[r * 512 + d] = c.v[(d * mul + add) & 2047];
    }
  }
};
struct alignas(1024) ET {
  uint16_t v[2048 * 128];
  constexpr ET() : v() {
    CosT c;
    for (int s = 0; s < 2048; s++)
      for (int j = 0; j < 64; j++) { v[s * 128 + j] = c.v[(s * j) & 2047]; v[s * 128 + 64 + j] = c.v[(s * j + 512) & 2047]; }
  }
};
struct alignas(1024) DT {
  uint16_t v[64 * 64];
  constexpr DT() : v() {
    CosT c;
    for (int r = 0; r < 64; r++)
      for (int n = 0; n < 64; n++) {
        const int sg = r >> 1, s0 = (sg & ~6) | ((sg & 2) << 1) | ((sg & 4) >> 1), e = r & 1, f = n & 1;
        const int m = 64 * s0 * (n >> 1) + (e == f ? 0 : e ? -512 : 512);
        v[r * 64 + (((n >> 3) ^ (r & 7)) << 3) + (n & 7)] = c.v[m & 2047];
      }
  }
};
}

__device__ constexpr tbl::FT g_FT = tbl::FT();
__device__ constexpr tbl::ET g_ET = tbl::ET();
__device__ constexpr tbl::DT g_DT = tbl::DT();

__device__ __align__(1024) uint16_t g_X[129 * 8192];
__device__ __align__(1024) uint16_t g_T[32 * 64 * 512];
__device__ __align__(1024) uint2 g_Ts[32 * 64];
__device__ __align__(1024) uint4 g_part[128 * 3 * 1024];
__device__ __align__(16) float g_gate[16 * 128];
__device__ __align__(16) uint2 g_Wh[2 * 2048];
__device__ unsigned g_epoch[132 * 8];
__device__ unsigned g_cntX[8 * 32], g_cntT[8 * 32], g_cntP[128 * 32], g_cntW[32], g_cntH[32];
#define PROF_EV(i) do {} while (0)
#define PROF_CK(i) do {} while (0)

__device__ __forceinline__ uint32_t smem_u32(const void* p) { return (uint32_t)__cvta_generic_to_shared(p); }
__device__ __forceinline__ void mbar_init(uint32_t bar, uint32_t cnt) { asm volatile("mbarrier.init.shared::cta.b64 [%0], %1;" ::"r"(bar), "r"(cnt)); }
__device__ __forceinline__ void mbar_expect_tx(uint32_t bar, uint32_t bytes) { asm volatile("mbarrier.arrive.expect_tx.shared::cta.b64 _, [%0], %1;" ::"r"(bar), "r"(bytes) : "memory"); }
__device__ __forceinline__ void mbar_arrive(uint32_t bar) { asm volatile("mbarrier.arrive.shared::cta.b64 _, [%0];" ::"r"(bar) : "memory"); }
__device__ __forceinline__ void mbar_wait(uint32_t bar, uint32_t parity) {
  asm volatile(
      "{\n.reg .pred p;\n.reg .u32 n;\nmov.u32 n, 0;\n"
      "W_LOOP:\nmbarrier.try_wait.parity.shared::cta.b64 p, [%0], %1;\n@p bra W_DONE;\n"
      "add.u32 n, n, 1;\nsetp.lt.u32 p, n, 0x40000;\n@p bra W_LOOP;\ntrap;\nW_DONE:\n}" ::"r"(bar), "r"(parity) : "memory");
}
__device__ __forceinline__ void bulk_load(uint32_t dst, const void* src, uint32_t bytes, uint32_t bar) {
  asm volatile("cp.async.bulk.shared::cluster.global.mbarrier::complete_tx::bytes [%0], [%1], %2, [%3];" ::"r"(dst), "l"(src), "r"(bytes), "r"(bar) : "memory");
}
__device__ __forceinline__ void cp16(uint32_t dst, const void* src) { asm volatile("cp.async.cg.shared.global [%0], [%1], 16;" ::"r"(dst), "l"(src) : "memory"); }
__device__ __forceinline__ void spin_guard(uint32_t t0) { if ((uint32_t)clock() - t0 > (1u << 30)) __trap(); }
__device__ __forceinline__ float tagf(float v, uint32_t tag) { return __uint_as_float((__float_as_uint(v) & ~1u) | tag); }
__device__ __forceinline__ float untag(float v) { return __uint_as_float(__float_as_uint(v) & ~1u); }
__device__ __forceinline__ void st_x2(float2* p, float a, float b) { asm volatile("st.relaxed.gpu.global.v2.f32 [%0], {%1,%2};" ::"l"(p), "f"(a), "f"(b) : "memory"); }
__device__ __forceinline__ float2 ld_x2(const float2* p) { float2 v; asm volatile("ld.relaxed.gpu.global.v2.f32 {%0,%1}, [%2];" : "=f"(v.x), "=f"(v.y) : "l"(p) : "memory"); return v; }
__device__ __forceinline__ void st_u2(uint2* p, uint32_t a, uint32_t b) { asm volatile("st.relaxed.gpu.global.v2.u32 [%0], {%1,%2};" ::"l"(p), "r"(a), "r"(b) : "memory"); }
__device__ __forceinline__ void prefetch2d(const CUtensorMap* m, int c0, int c1) { asm volatile("cp.async.bulk.prefetch.tensor.2d.L2.global [%0, {%1, %2}];" ::"l"(m), "r"(c0), "r"(c1) : "memory"); }
__device__ __forceinline__ void prefetch1d(const void* p, uint32_t bytes) { asm volatile("cp.async.bulk.prefetch.L2.global [%0], %1;" ::"l"(p), "r"(bytes) : "memory"); }
__device__ __forceinline__ uint32_t ld_x1(const void* p) { uint32_t v; asm volatile("ld.relaxed.gpu.global.u32 %0, [%1];" : "=r"(v) : "l"(p) : "memory"); return v; }
__device__ __forceinline__ uint4 ld_x4(const void* p) { uint4 v; asm volatile("ld.relaxed.gpu.global.v4.u32 {%0,%1,%2,%3}, [%4];" : "=r"(v.x), "=r"(v.y), "=r"(v.z), "=r"(v.w) : "l"(p) : "memory"); return v; }
__device__ __forceinline__ void st_x4(void* p, uint32_t a, uint32_t b, uint32_t c, uint32_t d) { asm volatile("st.relaxed.gpu.global.v4.u32 [%0], {%1,%2,%3,%4};" ::"l"(p), "r"(a), "r"(b), "r"(c), "r"(d) : "memory"); }
__device__ __forceinline__ uint32_t mapa(uint32_t a, uint32_t cta) { uint32_t r; asm volatile("mapa.shared::cluster.u32 %0, %1, %2;" : "=r"(r) : "r"(a), "r"(cta)); return r; }
__device__ __forceinline__ void stsm4t(uint32_t a, uint32_t r0, uint32_t r1, uint32_t r2, uint32_t r3) {
  asm volatile("stmatrix.sync.aligned.m8n8.x4.trans.shared.b16 [%0], {%1,%2,%3,%4};" ::"r"(a), "r"(r0), "r"(r1), "r"(r2), "r"(r3) : "memory");
}
__device__ __forceinline__ void hint_add(unsigned* p) { asm volatile("red.relaxed.gpu.global.add.u32 [%0], 1;" ::"l"(p) : "memory"); }
__device__ __forceinline__ void hint_wait(const unsigned* p, unsigned target) {
  const uint32_t t0 = (uint32_t)clock();
  while ((int)(ld_x1(p) - target) < 0) spin_guard(t0);
}
__device__ __forceinline__ void bulk_done_signal(unsigned* p) {
  asm volatile("cp.async.bulk.commit_group;\ncp.async.bulk.wait_group 0;\nfence.proxy.async.global;" ::: "memory");
  hint_add(p);
}
__device__ __forceinline__ void flag_wait(const unsigned* p, unsigned target) {
  hint_wait(p, target);
  asm volatile("fence.proxy.async.global;" ::: "memory");
}
__device__ __forceinline__ void tma2d(uint32_t dst, const CUtensorMap* m, uint32_t bar, int c0, int c1) {
  asm volatile("cp.async.bulk.tensor.2d.shared::cluster.global.mbarrier::complete_tx::bytes [%0], [%1, {%3, %4}], [%2];" ::"r"(dst), "l"(m), "r"(bar), "r"(c0), "r"(c1) : "memory");
}
__device__ __forceinline__ void tma3d(uint32_t dst, const CUtensorMap* m, uint32_t bar, int c0, int c1, int c2) {
  asm volatile("cp.async.bulk.tensor.3d.shared::cluster.global.mbarrier::complete_tx::bytes [%0], [%1, {%3, %4, %5}], [%2];" ::"r"(dst), "l"(m), "r"(bar), "r"(c0), "r"(c1), "r"(c2) : "memory");
}
__device__ __forceinline__ void tma4d(uint32_t dst, const CUtensorMap* m, uint32_t bar, int c0, int c1, int c2, int c3) {
  asm volatile("cp.async.bulk.tensor.4d.shared::cluster.global.mbarrier::complete_tx::bytes [%0], [%1, {%3, %4, %5, %6}], [%2];" ::"r"(dst), "l"(m), "r"(bar), "r"(c0), "r"(c1), "r"(c2), "r"(c3) : "memory");
}
__device__ __forceinline__ void wg_fence() { asm volatile("wgmma.fence.sync.aligned;" ::: "memory"); }
__device__ __forceinline__ void wg_commit() { asm volatile("wgmma.commit_group.sync.aligned;" ::: "memory"); }
template <int N> __device__ __forceinline__ void wg_wait() { asm volatile("wgmma.wait_group.sync.aligned %0;" ::"n"(N) : "memory"); }
template <int O, int N, int NN> __device__ __forceinline__ void fence_regs(float (&d)[NN]) {
#pragma unroll
  for (int i = 0; i < N; i++) asm volatile("" : "+f"(d[O + i])::"memory");
}
__device__ __forceinline__ uint32_t pack_bf16(float lo, float hi) {
  uint32_t r; asm("cvt.rn.bf16x2.f32 %0, %1, %2;" : "=r"(r) : "f"(hi), "f"(lo)); return r;
}
__device__ __forceinline__ uint32_t pack_pin(float lo, float hi) {
  uint32_t r; asm volatile("cvt.rn.bf16x2.f32 %0, %1, %2;" : "=r"(r) : "f"(hi), "f"(lo) : "memory"); return r;
}
__device__ __forceinline__ float bf_lo(uint32_t u) { return __uint_as_float(u << 16); }
__device__ __forceinline__ float bf_hi(uint32_t u) { return __uint_as_float(u & 0xffff0000u); }

__device__ __forceinline__ uint64_t d128(uint32_t lo) { uint64_t d; asm("mov.b64 %0, {%1, 0x40000040};" : "=l"(d) : "r"(lo)); return d; }
__device__ __forceinline__ uint64_t d64(uint32_t lo) { uint64_t d; asm("mov.b64 %0, {%1, 0x80000020};" : "=l"(d) : "r"(lo)); return d; }
template<int O,int TB,int ACC,int NN> __device__ __forceinline__ void mma_ss64(float (&d)[NN], uint64_t da, uint64_t db, int sd = 0){
  if constexpr (ACC == 1) asm volatile("wgmma.mma_async.sync.aligned.m64n64k16.f32.bf16.bf16 {%0,%1,%2,%3,%4,%5,%6,%7,%8,%9,%10,%11,%12,%13,%14,%15,%16,%17,%18,%19,%20,%21,%22,%23,%24,%25,%26,%27,%28,%29,%30,%31}, %32, %33, 1, 1, 1, %35, %34;"
   : "+f"(d[O+0]), "+f"(d[O+1]), "+f"(d[O+2]), "+f"(d[O+3]), "+f"(d[O+4]), "+f"(d[O+5]), "+f"(d[O+6]), "+f"(d[O+7]), "+f"(d[O+8]), "+f"(d[O+9]), "+f"(d[O+10]), "+f"(d[O+11]), "+f"(d[O+12]), "+f"(d[O+13]), "+f"(d[O+14]), "+f"(d[O+15]), "+f"(d[O+16]), "+f"(d[O+17]), "+f"(d[O+18]), "+f"(d[O+19]), "+f"(d[O+20]), "+f"(d[O+21]), "+f"(d[O+22]), "+f"(d[O+23]), "+f"(d[O+24]), "+f"(d[O+25]), "+f"(d[O+26]), "+f"(d[O+27]), "+f"(d[O+28]), "+f"(d[O+29]), "+f"(d[O+30]), "+f"(d[O+31])
   : "l"(da), "l"(db), "n"(TB & 1), "n"(TB >> 1));
  else if constexpr (ACC == 0) asm volatile("wgmma.mma_async.sync.aligned.m64n64k16.f32.bf16.bf16 {%0,%1,%2,%3,%4,%5,%6,%7,%8,%9,%10,%11,%12,%13,%14,%15,%16,%17,%18,%19,%20,%21,%22,%23,%24,%25,%26,%27,%28,%29,%30,%31}, %32, %33, 0, 1, 1, %35, %34;"
   : "=f"(d[O+0]), "=f"(d[O+1]), "=f"(d[O+2]), "=f"(d[O+3]), "=f"(d[O+4]), "=f"(d[O+5]), "=f"(d[O+6]), "=f"(d[O+7]), "=f"(d[O+8]), "=f"(d[O+9]), "=f"(d[O+10]), "=f"(d[O+11]), "=f"(d[O+12]), "=f"(d[O+13]), "=f"(d[O+14]), "=f"(d[O+15]), "=f"(d[O+16]), "=f"(d[O+17]), "=f"(d[O+18]), "=f"(d[O+19]), "=f"(d[O+20]), "=f"(d[O+21]), "=f"(d[O+22]), "=f"(d[O+23]), "=f"(d[O+24]), "=f"(d[O+25]), "=f"(d[O+26]), "=f"(d[O+27]), "=f"(d[O+28]), "=f"(d[O+29]), "=f"(d[O+30]), "=f"(d[O+31])
   : "l"(da), "l"(db), "n"(TB & 1), "n"(TB >> 1));
  else asm volatile("{\n.reg .pred p;\nsetp.ne.b32 p, %36, 0;\nwgmma.mma_async.sync.aligned.m64n64k16.f32.bf16.bf16 {%0,%1,%2,%3,%4,%5,%6,%7,%8,%9,%10,%11,%12,%13,%14,%15,%16,%17,%18,%19,%20,%21,%22,%23,%24,%25,%26,%27,%28,%29,%30,%31}, %32, %33, p, 1, 1, %35, %34;\n}"
   : "+f"(d[O+0]), "+f"(d[O+1]), "+f"(d[O+2]), "+f"(d[O+3]), "+f"(d[O+4]), "+f"(d[O+5]), "+f"(d[O+6]), "+f"(d[O+7]), "+f"(d[O+8]), "+f"(d[O+9]), "+f"(d[O+10]), "+f"(d[O+11]), "+f"(d[O+12]), "+f"(d[O+13]), "+f"(d[O+14]), "+f"(d[O+15]), "+f"(d[O+16]), "+f"(d[O+17]), "+f"(d[O+18]), "+f"(d[O+19]), "+f"(d[O+20]), "+f"(d[O+21]), "+f"(d[O+22]), "+f"(d[O+23]), "+f"(d[O+24]), "+f"(d[O+25]), "+f"(d[O+26]), "+f"(d[O+27]), "+f"(d[O+28]), "+f"(d[O+29]), "+f"(d[O+30]), "+f"(d[O+31])
   : "l"(da), "l"(db), "n"(TB & 1), "n"(TB >> 1), "r"(sd));
}
template<int O,int TB,int ACC,int NN> __device__ __forceinline__ void mma_rs64(float (&d)[NN], uint32_t a0, uint32_t a1, uint32_t a2, uint32_t a3, uint64_t db, int sd = 0){
  if constexpr (ACC == 1) asm volatile("wgmma.mma_async.sync.aligned.m64n64k16.f32.bf16.bf16 {%0,%1,%2,%3,%4,%5,%6,%7,%8,%9,%10,%11,%12,%13,%14,%15,%16,%17,%18,%19,%20,%21,%22,%23,%24,%25,%26,%27,%28,%29,%30,%31}, {%32,%33,%34,%35}, %36, 1, 1, 1, %37;"
   : "+f"(d[O+0]), "+f"(d[O+1]), "+f"(d[O+2]), "+f"(d[O+3]), "+f"(d[O+4]), "+f"(d[O+5]), "+f"(d[O+6]), "+f"(d[O+7]), "+f"(d[O+8]), "+f"(d[O+9]), "+f"(d[O+10]), "+f"(d[O+11]), "+f"(d[O+12]), "+f"(d[O+13]), "+f"(d[O+14]), "+f"(d[O+15]), "+f"(d[O+16]), "+f"(d[O+17]), "+f"(d[O+18]), "+f"(d[O+19]), "+f"(d[O+20]), "+f"(d[O+21]), "+f"(d[O+22]), "+f"(d[O+23]), "+f"(d[O+24]), "+f"(d[O+25]), "+f"(d[O+26]), "+f"(d[O+27]), "+f"(d[O+28]), "+f"(d[O+29]), "+f"(d[O+30]), "+f"(d[O+31])
   : "r"(a0), "r"(a1), "r"(a2), "r"(a3), "l"(db), "n"(TB));
  else if constexpr (ACC == 0) asm volatile("wgmma.mma_async.sync.aligned.m64n64k16.f32.bf16.bf16 {%0,%1,%2,%3,%4,%5,%6,%7,%8,%9,%10,%11,%12,%13,%14,%15,%16,%17,%18,%19,%20,%21,%22,%23,%24,%25,%26,%27,%28,%29,%30,%31}, {%32,%33,%34,%35}, %36, 0, 1, 1, %37;"
   : "=f"(d[O+0]), "=f"(d[O+1]), "=f"(d[O+2]), "=f"(d[O+3]), "=f"(d[O+4]), "=f"(d[O+5]), "=f"(d[O+6]), "=f"(d[O+7]), "=f"(d[O+8]), "=f"(d[O+9]), "=f"(d[O+10]), "=f"(d[O+11]), "=f"(d[O+12]), "=f"(d[O+13]), "=f"(d[O+14]), "=f"(d[O+15]), "=f"(d[O+16]), "=f"(d[O+17]), "=f"(d[O+18]), "=f"(d[O+19]), "=f"(d[O+20]), "=f"(d[O+21]), "=f"(d[O+22]), "=f"(d[O+23]), "=f"(d[O+24]), "=f"(d[O+25]), "=f"(d[O+26]), "=f"(d[O+27]), "=f"(d[O+28]), "=f"(d[O+29]), "=f"(d[O+30]), "=f"(d[O+31])
   : "r"(a0), "r"(a1), "r"(a2), "r"(a3), "l"(db), "n"(TB));
  else asm volatile("{\n.reg .pred p;\nsetp.ne.b32 p, %38, 0;\nwgmma.mma_async.sync.aligned.m64n64k16.f32.bf16.bf16 {%0,%1,%2,%3,%4,%5,%6,%7,%8,%9,%10,%11,%12,%13,%14,%15,%16,%17,%18,%19,%20,%21,%22,%23,%24,%25,%26,%27,%28,%29,%30,%31}, {%32,%33,%34,%35}, %36, p, 1, 1, %37;\n}"
   : "+f"(d[O+0]), "+f"(d[O+1]), "+f"(d[O+2]), "+f"(d[O+3]), "+f"(d[O+4]), "+f"(d[O+5]), "+f"(d[O+6]), "+f"(d[O+7]), "+f"(d[O+8]), "+f"(d[O+9]), "+f"(d[O+10]), "+f"(d[O+11]), "+f"(d[O+12]), "+f"(d[O+13]), "+f"(d[O+14]), "+f"(d[O+15]), "+f"(d[O+16]), "+f"(d[O+17]), "+f"(d[O+18]), "+f"(d[O+19]), "+f"(d[O+20]), "+f"(d[O+21]), "+f"(d[O+22]), "+f"(d[O+23]), "+f"(d[O+24]), "+f"(d[O+25]), "+f"(d[O+26]), "+f"(d[O+27]), "+f"(d[O+28]), "+f"(d[O+29]), "+f"(d[O+30]), "+f"(d[O+31])
   : "r"(a0), "r"(a1), "r"(a2), "r"(a3), "l"(db), "n"(TB), "r"(sd));
}
template<int O,int TB,int ACC,int NN> __device__ __forceinline__ void mma_ss128(float (&d)[NN], uint64_t da, uint64_t db, int sd = 0){
  if constexpr (ACC == 1) asm volatile("wgmma.mma_async.sync.aligned.m64n128k16.f32.bf16.bf16 {%0,%1,%2,%3,%4,%5,%6,%7,%8,%9,%10,%11,%12,%13,%14,%15,%16,%17,%18,%19,%20,%21,%22,%23,%24,%25,%26,%27,%28,%29,%30,%31,%32,%33,%34,%35,%36,%37,%38,%39,%40,%41,%42,%43,%44,%45,%46,%47,%48,%49,%50,%51,%52,%53,%54,%55,%56,%57,%58,%59,%60,%61,%62,%63}, %64, %65, 1, 1, 1, %67, %66;"
   : "+f"(d[O+0]), "+f"(d[O+1]), "+f"(d[O+2]), "+f"(d[O+3]), "+f"(d[O+4]), "+f"(d[O+5]), "+f"(d[O+6]), "+f"(d[O+7]), "+f"(d[O+8]), "+f"(d[O+9]), "+f"(d[O+10]), "+f"(d[O+11]), "+f"(d[O+12]), "+f"(d[O+13]), "+f"(d[O+14]), "+f"(d[O+15]), "+f"(d[O+16]), "+f"(d[O+17]), "+f"(d[O+18]), "+f"(d[O+19]), "+f"(d[O+20]), "+f"(d[O+21]), "+f"(d[O+22]), "+f"(d[O+23]), "+f"(d[O+24]), "+f"(d[O+25]), "+f"(d[O+26]), "+f"(d[O+27]), "+f"(d[O+28]), "+f"(d[O+29]), "+f"(d[O+30]), "+f"(d[O+31]), "+f"(d[O+32]), "+f"(d[O+33]), "+f"(d[O+34]), "+f"(d[O+35]), "+f"(d[O+36]), "+f"(d[O+37]), "+f"(d[O+38]), "+f"(d[O+39]), "+f"(d[O+40]), "+f"(d[O+41]), "+f"(d[O+42]), "+f"(d[O+43]), "+f"(d[O+44]), "+f"(d[O+45]), "+f"(d[O+46]), "+f"(d[O+47]), "+f"(d[O+48]), "+f"(d[O+49]), "+f"(d[O+50]), "+f"(d[O+51]), "+f"(d[O+52]), "+f"(d[O+53]), "+f"(d[O+54]), "+f"(d[O+55]), "+f"(d[O+56]), "+f"(d[O+57]), "+f"(d[O+58]), "+f"(d[O+59]), "+f"(d[O+60]), "+f"(d[O+61]), "+f"(d[O+62]), "+f"(d[O+63])
   : "l"(da), "l"(db), "n"(TB & 1), "n"(TB >> 1));
  else if constexpr (ACC == 0) asm volatile("wgmma.mma_async.sync.aligned.m64n128k16.f32.bf16.bf16 {%0,%1,%2,%3,%4,%5,%6,%7,%8,%9,%10,%11,%12,%13,%14,%15,%16,%17,%18,%19,%20,%21,%22,%23,%24,%25,%26,%27,%28,%29,%30,%31,%32,%33,%34,%35,%36,%37,%38,%39,%40,%41,%42,%43,%44,%45,%46,%47,%48,%49,%50,%51,%52,%53,%54,%55,%56,%57,%58,%59,%60,%61,%62,%63}, %64, %65, 0, 1, 1, %67, %66;"
   : "=f"(d[O+0]), "=f"(d[O+1]), "=f"(d[O+2]), "=f"(d[O+3]), "=f"(d[O+4]), "=f"(d[O+5]), "=f"(d[O+6]), "=f"(d[O+7]), "=f"(d[O+8]), "=f"(d[O+9]), "=f"(d[O+10]), "=f"(d[O+11]), "=f"(d[O+12]), "=f"(d[O+13]), "=f"(d[O+14]), "=f"(d[O+15]), "=f"(d[O+16]), "=f"(d[O+17]), "=f"(d[O+18]), "=f"(d[O+19]), "=f"(d[O+20]), "=f"(d[O+21]), "=f"(d[O+22]), "=f"(d[O+23]), "=f"(d[O+24]), "=f"(d[O+25]), "=f"(d[O+26]), "=f"(d[O+27]), "=f"(d[O+28]), "=f"(d[O+29]), "=f"(d[O+30]), "=f"(d[O+31]), "=f"(d[O+32]), "=f"(d[O+33]), "=f"(d[O+34]), "=f"(d[O+35]), "=f"(d[O+36]), "=f"(d[O+37]), "=f"(d[O+38]), "=f"(d[O+39]), "=f"(d[O+40]), "=f"(d[O+41]), "=f"(d[O+42]), "=f"(d[O+43]), "=f"(d[O+44]), "=f"(d[O+45]), "=f"(d[O+46]), "=f"(d[O+47]), "=f"(d[O+48]), "=f"(d[O+49]), "=f"(d[O+50]), "=f"(d[O+51]), "=f"(d[O+52]), "=f"(d[O+53]), "=f"(d[O+54]), "=f"(d[O+55]), "=f"(d[O+56]), "=f"(d[O+57]), "=f"(d[O+58]), "=f"(d[O+59]), "=f"(d[O+60]), "=f"(d[O+61]), "=f"(d[O+62]), "=f"(d[O+63])
   : "l"(da), "l"(db), "n"(TB & 1), "n"(TB >> 1));
  else asm volatile("{\n.reg .pred p;\nsetp.ne.b32 p, %68, 0;\nwgmma.mma_async.sync.aligned.m64n128k16.f32.bf16.bf16 {%0,%1,%2,%3,%4,%5,%6,%7,%8,%9,%10,%11,%12,%13,%14,%15,%16,%17,%18,%19,%20,%21,%22,%23,%24,%25,%26,%27,%28,%29,%30,%31,%32,%33,%34,%35,%36,%37,%38,%39,%40,%41,%42,%43,%44,%45,%46,%47,%48,%49,%50,%51,%52,%53,%54,%55,%56,%57,%58,%59,%60,%61,%62,%63}, %64, %65, p, 1, 1, %67, %66;\n}"
   : "+f"(d[O+0]), "+f"(d[O+1]), "+f"(d[O+2]), "+f"(d[O+3]), "+f"(d[O+4]), "+f"(d[O+5]), "+f"(d[O+6]), "+f"(d[O+7]), "+f"(d[O+8]), "+f"(d[O+9]), "+f"(d[O+10]), "+f"(d[O+11]), "+f"(d[O+12]), "+f"(d[O+13]), "+f"(d[O+14]), "+f"(d[O+15]), "+f"(d[O+16]), "+f"(d[O+17]), "+f"(d[O+18]), "+f"(d[O+19]), "+f"(d[O+20]), "+f"(d[O+21]), "+f"(d[O+22]), "+f"(d[O+23]), "+f"(d[O+24]), "+f"(d[O+25]), "+f"(d[O+26]), "+f"(d[O+27]), "+f"(d[O+28]), "+f"(d[O+29]), "+f"(d[O+30]), "+f"(d[O+31]), "+f"(d[O+32]), "+f"(d[O+33]), "+f"(d[O+34]), "+f"(d[O+35]), "+f"(d[O+36]), "+f"(d[O+37]), "+f"(d[O+38]), "+f"(d[O+39]), "+f"(d[O+40]), "+f"(d[O+41]), "+f"(d[O+42]), "+f"(d[O+43]), "+f"(d[O+44]), "+f"(d[O+45]), "+f"(d[O+46]), "+f"(d[O+47]), "+f"(d[O+48]), "+f"(d[O+49]), "+f"(d[O+50]), "+f"(d[O+51]), "+f"(d[O+52]), "+f"(d[O+53]), "+f"(d[O+54]), "+f"(d[O+55]), "+f"(d[O+56]), "+f"(d[O+57]), "+f"(d[O+58]), "+f"(d[O+59]), "+f"(d[O+60]), "+f"(d[O+61]), "+f"(d[O+62]), "+f"(d[O+63])
   : "l"(da), "l"(db), "n"(TB & 1), "n"(TB >> 1), "r"(sd));
}
template<int O,int TB,int ACC,int NN> __device__ __forceinline__ void mma_rs128(float (&d)[NN], uint32_t a0, uint32_t a1, uint32_t a2, uint32_t a3, uint64_t db, int sd = 0){
  if constexpr (ACC == 1) asm volatile("wgmma.mma_async.sync.aligned.m64n128k16.f32.bf16.bf16 {%0,%1,%2,%3,%4,%5,%6,%7,%8,%9,%10,%11,%12,%13,%14,%15,%16,%17,%18,%19,%20,%21,%22,%23,%24,%25,%26,%27,%28,%29,%30,%31,%32,%33,%34,%35,%36,%37,%38,%39,%40,%41,%42,%43,%44,%45,%46,%47,%48,%49,%50,%51,%52,%53,%54,%55,%56,%57,%58,%59,%60,%61,%62,%63}, {%64,%65,%66,%67}, %68, 1, 1, 1, %69;"
   : "+f"(d[O+0]), "+f"(d[O+1]), "+f"(d[O+2]), "+f"(d[O+3]), "+f"(d[O+4]), "+f"(d[O+5]), "+f"(d[O+6]), "+f"(d[O+7]), "+f"(d[O+8]), "+f"(d[O+9]), "+f"(d[O+10]), "+f"(d[O+11]), "+f"(d[O+12]), "+f"(d[O+13]), "+f"(d[O+14]), "+f"(d[O+15]), "+f"(d[O+16]), "+f"(d[O+17]), "+f"(d[O+18]), "+f"(d[O+19]), "+f"(d[O+20]), "+f"(d[O+21]), "+f"(d[O+22]), "+f"(d[O+23]), "+f"(d[O+24]), "+f"(d[O+25]), "+f"(d[O+26]), "+f"(d[O+27]), "+f"(d[O+28]), "+f"(d[O+29]), "+f"(d[O+30]), "+f"(d[O+31]), "+f"(d[O+32]), "+f"(d[O+33]), "+f"(d[O+34]), "+f"(d[O+35]), "+f"(d[O+36]), "+f"(d[O+37]), "+f"(d[O+38]), "+f"(d[O+39]), "+f"(d[O+40]), "+f"(d[O+41]), "+f"(d[O+42]), "+f"(d[O+43]), "+f"(d[O+44]), "+f"(d[O+45]), "+f"(d[O+46]), "+f"(d[O+47]), "+f"(d[O+48]), "+f"(d[O+49]), "+f"(d[O+50]), "+f"(d[O+51]), "+f"(d[O+52]), "+f"(d[O+53]), "+f"(d[O+54]), "+f"(d[O+55]), "+f"(d[O+56]), "+f"(d[O+57]), "+f"(d[O+58]), "+f"(d[O+59]), "+f"(d[O+60]), "+f"(d[O+61]), "+f"(d[O+62]), "+f"(d[O+63])
   : "r"(a0), "r"(a1), "r"(a2), "r"(a3), "l"(db), "n"(TB));
  else if constexpr (ACC == 0) asm volatile("wgmma.mma_async.sync.aligned.m64n128k16.f32.bf16.bf16 {%0,%1,%2,%3,%4,%5,%6,%7,%8,%9,%10,%11,%12,%13,%14,%15,%16,%17,%18,%19,%20,%21,%22,%23,%24,%25,%26,%27,%28,%29,%30,%31,%32,%33,%34,%35,%36,%37,%38,%39,%40,%41,%42,%43,%44,%45,%46,%47,%48,%49,%50,%51,%52,%53,%54,%55,%56,%57,%58,%59,%60,%61,%62,%63}, {%64,%65,%66,%67}, %68, 0, 1, 1, %69;"
   : "=f"(d[O+0]), "=f"(d[O+1]), "=f"(d[O+2]), "=f"(d[O+3]), "=f"(d[O+4]), "=f"(d[O+5]), "=f"(d[O+6]), "=f"(d[O+7]), "=f"(d[O+8]), "=f"(d[O+9]), "=f"(d[O+10]), "=f"(d[O+11]), "=f"(d[O+12]), "=f"(d[O+13]), "=f"(d[O+14]), "=f"(d[O+15]), "=f"(d[O+16]), "=f"(d[O+17]), "=f"(d[O+18]), "=f"(d[O+19]), "=f"(d[O+20]), "=f"(d[O+21]), "=f"(d[O+22]), "=f"(d[O+23]), "=f"(d[O+24]), "=f"(d[O+25]), "=f"(d[O+26]), "=f"(d[O+27]), "=f"(d[O+28]), "=f"(d[O+29]), "=f"(d[O+30]), "=f"(d[O+31]), "=f"(d[O+32]), "=f"(d[O+33]), "=f"(d[O+34]), "=f"(d[O+35]), "=f"(d[O+36]), "=f"(d[O+37]), "=f"(d[O+38]), "=f"(d[O+39]), "=f"(d[O+40]), "=f"(d[O+41]), "=f"(d[O+42]), "=f"(d[O+43]), "=f"(d[O+44]), "=f"(d[O+45]), "=f"(d[O+46]), "=f"(d[O+47]), "=f"(d[O+48]), "=f"(d[O+49]), "=f"(d[O+50]), "=f"(d[O+51]), "=f"(d[O+52]), "=f"(d[O+53]), "=f"(d[O+54]), "=f"(d[O+55]), "=f"(d[O+56]), "=f"(d[O+57]), "=f"(d[O+58]), "=f"(d[O+59]), "=f"(d[O+60]), "=f"(d[O+61]), "=f"(d[O+62]), "=f"(d[O+63])
   : "r"(a0), "r"(a1), "r"(a2), "r"(a3), "l"(db), "n"(TB));
  else asm volatile("{\n.reg .pred p;\nsetp.ne.b32 p, %70, 0;\nwgmma.mma_async.sync.aligned.m64n128k16.f32.bf16.bf16 {%0,%1,%2,%3,%4,%5,%6,%7,%8,%9,%10,%11,%12,%13,%14,%15,%16,%17,%18,%19,%20,%21,%22,%23,%24,%25,%26,%27,%28,%29,%30,%31,%32,%33,%34,%35,%36,%37,%38,%39,%40,%41,%42,%43,%44,%45,%46,%47,%48,%49,%50,%51,%52,%53,%54,%55,%56,%57,%58,%59,%60,%61,%62,%63}, {%64,%65,%66,%67}, %68, p, 1, 1, %69;\n}"
   : "+f"(d[O+0]), "+f"(d[O+1]), "+f"(d[O+2]), "+f"(d[O+3]), "+f"(d[O+4]), "+f"(d[O+5]), "+f"(d[O+6]), "+f"(d[O+7]), "+f"(d[O+8]), "+f"(d[O+9]), "+f"(d[O+10]), "+f"(d[O+11]), "+f"(d[O+12]), "+f"(d[O+13]), "+f"(d[O+14]), "+f"(d[O+15]), "+f"(d[O+16]), "+f"(d[O+17]), "+f"(d[O+18]), "+f"(d[O+19]), "+f"(d[O+20]), "+f"(d[O+21]), "+f"(d[O+22]), "+f"(d[O+23]), "+f"(d[O+24]), "+f"(d[O+25]), "+f"(d[O+26]), "+f"(d[O+27]), "+f"(d[O+28]), "+f"(d[O+29]), "+f"(d[O+30]), "+f"(d[O+31]), "+f"(d[O+32]), "+f"(d[O+33]), "+f"(d[O+34]), "+f"(d[O+35]), "+f"(d[O+36]), "+f"(d[O+37]), "+f"(d[O+38]), "+f"(d[O+39]), "+f"(d[O+40]), "+f"(d[O+41]), "+f"(d[O+42]), "+f"(d[O+43]), "+f"(d[O+44]), "+f"(d[O+45]), "+f"(d[O+46]), "+f"(d[O+47]), "+f"(d[O+48]), "+f"(d[O+49]), "+f"(d[O+50]), "+f"(d[O+51]), "+f"(d[O+52]), "+f"(d[O+53]), "+f"(d[O+54]), "+f"(d[O+55]), "+f"(d[O+56]), "+f"(d[O+57]), "+f"(d[O+58]), "+f"(d[O+59]), "+f"(d[O+60]), "+f"(d[O+61]), "+f"(d[O+62]), "+f"(d[O+63])
   : "r"(a0), "r"(a1), "r"(a2), "r"(a3), "l"(db), "n"(TB), "r"(sd));
}

#define NEARLY 0
#define XAHEAD 3
#define HM 2
#define SPACE 100
#define WAFTER 7
#define WPACE 100
#define GATE_AT 4
#define TPACE 40
#define PFMODE 0
#define MAPMODE 0
template <int V> struct IC { static constexpr int value = V; };
struct Maps { CUtensorMap x, ft, g64, u64, e, wr, wi, xs, ts, t, g32, u32, d224; };

constexpr int NCTA = 130;
constexpr int U = 16384;
constexpr int TB = 36864;
constexpr int NR = 4;
constexpr int OFF_RING = 8 * U, OFF_Z = 9 * U, OFF_XB = 12 * U, OFF_T = 13 * U, OFF_D = OFF_T;
constexpr int OFF_BAR = 14 * U, OFF_SP = OFF_BAR + 512;
constexpr int SMEM_BYTES = OFF_SP + 1024;
constexpr int B_FX = 0, B_FA = 8, B_FT = 12, B_Z = 16, B_W = 20, B_HX = 21, B_TL = 22, B_HP = 23, B_WR = 26;
constexpr int B_EA = 30, B_ET = 34, B_RDY = 38, B_C1 = 39;
constexpr int B_T = 40, B_XS = 41, NBAR = 43;
__host__ __device__ constexpr int rslot(int n) { return n & 3; }
__host__ __device__ constexpr int rpar(int n) { return (n >> 2) & 1; }

__global__ void __cluster_dims__(2, 1, 1) __launch_bounds__(512, 1)
fused_kernel(const __grid_constant__ Maps maps, const __nv_bfloat16* __restrict__ x, const __nv_bfloat16* __restrict__ w_r,
             const __nv_bfloat16* __restrict__ w_i, const __nv_bfloat16* __restrict__ gate_w, __nv_bfloat16* __restrict__ out) {
  extern __shared__ __align__(1024) uint8_t smem[];
  const uint32_t sb = smem_u32(smem);
  const uint32_t bars = sb + OFF_BAR;
  const int tid = threadIdx.x, lane = tid & 31;
  const int warp = __shfl_sync(0xffffffffu, tid >> 5, 0);
  const bool helper = blockIdx.x >= 128;
  const int cl = (blockIdx.x >> 1) & 63, rank = blockIdx.x & 1;
  const int q4 = cl & 3, rb = cl >> 2;
  const int j = 2 * q4 + rank;
  const int f_full = 448 * q4 + (rank ? 256 : 0);
  const int f_half = 448 * q4 + (rank ? 224 : 192);
  const int kg = 2 * j + (rb >> 3), tn = rb & 7;

  if (tid == 64) { PROF_EV(0); PROF_CK(40); }
  auto ring_part = [&](int p, int n, int slot) {
    const uint32_t fb = bars + 8 * (B_FA + slot), dst = sb + OFF_RING + slot * U + p * 8192;
    const bool table = n == 8 || n == 9 || n >= 30;
    const int q = n < 8 ? n : n - 2;
    if (p == 0) {
      mbar_expect_tx(fb, n < 8 ? U + 8192 : U);
    }
    if (table) { if (p == 0) tma4d(dst, &maps.e, fb, 0, 0, 0, 2 * rb + (n & 1)); }
    else if (n >= 26) tma2d(dst, p ? &maps.u32 : &maps.g32, fb, f_half, 128 * (n - 26));
    else {
      if (n < 8 && p == 1) tma2d(sb + OFF_XB + slot * 8192, &maps.ft, fb, 64 * n, 64 * j);
      tma2d(dst, p ? &maps.u64 : &maps.g64, fb, f_full + 64 * (q >> 3), 64 * (q & 7));
    }
  };
  auto x_load = [&](int q) {
    mbar_expect_tx(bars + 8 * (B_FX + q), U);
    tma3d(sb + q * U, &maps.x, bars + 8 * (B_FX + q), 64 * q, 0, 2 * rb);
  };
  if (warp < 8) {
    asm volatile("barrier.cluster.arrive.relaxed.aligned;" ::: "memory");
    asm volatile("setmaxnreg.inc.sync.aligned.u32 192;");
    if (tid == 0) PROF_EV(33);
    if (!helper) {
      const int wg = warp >> 2, w = warp & 3, g = lane >> 2, q = lane & 3;
      const bool elect = (tid & 127) == 0;
      float cX[32], cA[64], cB[64], ci[64], ct[64];
      const int zero = blockIdx.x >> 16;
      uint32_t h[56], yf[16];
      const uint32_t d0 = (sb & 0x3FFFF) >> 4;
      const uint32_t dK = d0 | (1u << 16), dN = d0 | (512u << 16);
      const uint32_t dX = dK + wg * 512;
      constexpr uint32_t RING = OFF_RING >> 4;
      auto waitA = [&](int n) { mbar_wait(bars + 8 * (B_FA + rslot(n)), rpar(n)); };
      auto freeA = [&](int n) { if (elect) mbar_arrive(bars + 8 * (B_EA + rslot(n))); };
      auto nop = [](int) {};

      if (tid == 0) PROF_EV(34);
      asm volatile("bar.sync 0, 384;" ::: "memory");
      if (tid == 0) PROF_EV(35);
#pragma unroll 1
      for (int kb = 0; kb < 8; kb++) {
        mbar_wait(bars + 8 * (B_FX + kb), 0);
        if (tid == 0 && kb == 0) PROF_EV(36);
        waitA(kb);
        wg_fence();
        const uint64_t dx = d128(dX + kb * 1024), df = d128(dK + (OFF_XB >> 4) + rslot(kb) * 512), db = d128(dN + RING + rslot(kb) * 1024);
        mma_ss64<0, 0, 2>(cX, df, dx, kb);
        mma_ss64<0, 0, 1>(cX, df + 2, dx + 2);
        wg_commit(); wg_wait<1>();
        if (kb) freeA(kb - 1);
        mma_ss64<0, 0, 1>(cX, df + 4, dx + 4);
        mma_ss64<0, 0, 1>(cX, df + 6, dx + 6);
        wg_commit();
        mma_ss128<0, 1, 2>(cA, dx, db, kb);
#pragma unroll
        for (int k = 1; k < 4; k++) mma_ss128<0, 1, 1>(cA, dx + k * 2, db + k * 128);
        wg_commit();
        if (kb == 0 && tid == 0) PROF_EV(1);
      }
      wg_wait<1>();
      fence_regs<0, 32>(cX);
#pragma unroll
      for (int e = 0; e < 16; e++) yf[e] = pack_pin(cX[2 * e], cX[2 * e + 1]);
      if (tid == 0) PROF_EV(2);
      float o0 = 1.0f, o1 = 1.0f;
      auto glu = [&](auto scaled, auto& acc, int half, int ho, int i0, int i1) {
#pragma unroll
        for (int i = i0; i < i1; i++) {
          float a = fmaxf(acc[2 * i], 0.f) * acc[half + 2 * i], b = fmaxf(acc[2 * i + 1], 0.f) * acc[half + 1 + 2 * i];
          if (decltype(scaled)::value) { const float o = (i & 1) ? o1 : o0; a *= o; b *= o; }
          h[ho + i] = pack_pin(a, b);
        }
      };
      {
        waitA(8); waitA(9);
        const uint64_t de = d128(dN + RING + wg * 1024);
        wg_fence();
        mma_rs128<0, 1, 0>(cB, yf[0], yf[1], yf[2], yf[3], de);
        wg_commit();
        wg_wait<1>();
        freeA(7);
        if (elect) mbar_arrive(bars + 8 * B_C1);
        fence_regs<0, 64>(cA);
#pragma unroll
        for (int k = 1; k < 4; k++) { glu(IC<0>(), cA, 32, 0, 4 * k - 4, 4 * k); mma_rs128<0, 1, 1>(cB, yf[4 * k], yf[4 * k + 1], yf[4 * k + 2], yf[4 * k + 3], de + k * 128); }
        wg_commit();
        glu(IC<0>(), cA, 32, 0, 12, 16);
      }
      auto ffn_step = [&](auto first, float (&acc)[64], int n, int kb, auto done, auto work) {
        waitA(n);
        wg_fence();
        const uint64_t dx = d128(dX + kb * 1024), db = d128(dN + RING + rslot(n) * 1024);
        mma_ss128<0, 1, decltype(first)::value>(acc, dx, db, zero);
        wg_commit();
        wg_wait<1>();
        done();
#pragma unroll
        for (int k = 1; k < 4; k++) { work(k - 1); mma_ss128<0, 1, 1>(acc, dx + k * 2, db + k * 128); }
        wg_commit();
        work(3);
      };
      {
        const int s0 = 2 * rb + wg, kr = 2 * ((s0 & 1) | ((s0 & 4) >> 1));
        const int m = lane >> 3, r = lane & 7;
        const uint32_t a0 = sb + OFF_XB + wg * 8192 + (((w >> 1) * 8 + (m >> 1)) * 2 + (w & 1)) * 256 + (m & 1) * 128 + ((r ^ (kr + (m & 1))) << 4);
        ffn_step(IC<2>(), cA, 10, 0, [&] { freeA(8); freeA(9); fence_regs<0, 64>(cB); }, [&](int i) {
          stsm4t(a0 + i * 1024, pack_bf16(cB[8 * i] - cB[34 + 8 * i], cB[8 * i + 1] - cB[35 + 8 * i]),
                 pack_bf16(cB[32 + 8 * i] + cB[8 * i + 2], cB[33 + 8 * i] + cB[8 * i + 3]),
                 pack_bf16(cB[8 * i + 4] - cB[38 + 8 * i], cB[8 * i + 5] - cB[39 + 8 * i]),
                 pack_bf16(cB[36 + 8 * i] + cB[8 * i + 6], cB[37 + 8 * i] + cB[8 * i + 7]));
        });
        if (j == 0 && w == 0 && g == 0) {
#pragma unroll
          for (int n = 0; n < 8; n++)
#pragma unroll
            for (int ce = 0; ce < 4; ce++)
              *(uint32_t*)(smem + OFF_SP + wg * 512 + ce * 128 + ((n ^ (kr + (ce & 1))) << 4) + 4 * q) =
                  pack_bf16(cB[(ce & 1) * 32 + 4 * n + (ce & 2)], cB[(ce & 1) * 32 + 4 * n + (ce & 2) + 1]);
        }
        ffn_step(IC<1>(), cA, 11, 1, [&] { freeA(10); }, [&](int i) {
          if (i == 1) {
            asm volatile("fence.proxy.async.shared::cta;" ::: "memory");
            __syncwarp();
            if (lane == 0) mbar_arrive(bars + 8 * (B_XS + wg));
            if (tid == 0) PROF_EV(3);
          }
        });
      }
#pragma unroll 1
      for (int kb = 2; kb < 6; kb++) ffn_step(IC<1>(), cA, 10 + kb, kb, [&] { freeA(9 + kb); }, nop);
      const float* gp = g_gate + rb * 128 + wg * 64 + w * 16 + g;
      uint32_t gb0 = ld_x1(gp), gb1 = ld_x1(gp + 8), ep = ld_x1(&g_epoch[blockIdx.x * 8]);
#pragma unroll 1
      for (int kb = 6; kb < 8; kb++) ffn_step(IC<1>(), cA, 10 + kb, kb, [&] { freeA(9 + kb); }, nop);
      asm volatile("" : "+r"(ep), "+r"(gb0), "+r"(gb1)::"memory");
      const uint32_t tag = (ep + 1) & 1;
      {
        const uint32_t t0 = (uint32_t)clock();
        while (__any_sync(0xffffffffu, ((gb0 ^ tag) | (gb1 ^ tag)) & 1)) { gb0 = ld_x1(gp); gb1 = ld_x1(gp + 8); spin_guard(t0); }
      }
      const float g0 = __uint_as_float(gb0 & ~1u), g1 = __uint_as_float(gb1 & ~1u);
      o0 = 1.0f - g0; o1 = 1.0f - g1;
      ffn_step(IC<2>(), cB, 18, 0, [&] { freeA(17); fence_regs<0, 64>(cA); }, [&](int i) { glu(IC<1>(), cA, 32, 16, 2 * i, 2 * i + 2); });
      if (tid == 0) PROF_EV(4);
      ffn_step(IC<1>(), cB, 19, 1, [&] { freeA(18); }, [&](int i) { glu(IC<1>(), cA, 32, 16, 8 + 2 * i, 10 + 2 * i); });
      ffn_step(IC<1>(), cB, 20, 2, [&] { freeA(19); }, [&](int i) {
#pragma unroll
        for (int e = 4 * i; e < 4 * i + 4; e++) { const float o = (e & 1) ? o1 : o0; h[e] = pack_pin(bf_lo(h[e]) * o, bf_hi(h[e]) * o); }
      });
#pragma unroll 1
      for (int kb = 3; kb < 8; kb++) ffn_step(IC<1>(), cB, 18 + kb, kb, [&] { freeA(17 + kb); }, nop);
      if (tid == 0) PROF_EV(5);
      auto m_step = [&](auto first, int i, auto done, auto work) {
        waitA(26 + i);
        wg_fence();
        const uint64_t dx = d128(dX + i * 2048), dm = d64(dN + RING + rslot(26 + i) * 1024);
        mma_ss64<0, 1, decltype(first)::value>(ct, dx, dm);
        mma_ss64<0, 1, 1>(ct, dx + 2, dm + 64);
        wg_commit();
        wg_wait<1>();
        done();
#pragma unroll
        for (int k = 2; k < 8; k++) { if (k & 1) work(k / 2 - 1); mma_ss64<0, 1, 1>(ct, dx + ((k >> 2) * 1024 + (k & 3) * 2), dm + k * 64); }
        wg_commit();
        work(3);
      };
      auto freeT = [&](int t) { if (elect) mbar_arrive(bars + 8 * (B_ET + t)); };
      m_step(IC<0>(), 0, [&] { freeA(25); fence_regs<0, 64>(cB); }, [&](int i) { glu(IC<1>(), cB, 32, 32, 2 * i, 2 * i + 2); });
      m_step(IC<1>(), 1, [&] { freeA(26); freeT(0); }, [&](int i) { glu(IC<1>(), cB, 32, 32, 8 + 2 * i, 10 + 2 * i); });
      m_step(IC<1>(), 2, [&] { freeA(27); freeT(1); }, nop);
      m_step(IC<1>(), 3, [&] { freeT(2); }, nop);
      if (wg) waitA(31); else waitA(30);
      if (tid == 0) PROF_EV(6);
      mbar_wait(bars + 8 * (j == 0 ? B_T : B_TL), 0);
      if (tid == 0) PROF_EV(7);
      wg_fence();
      {
        const uint64_t dt = d128(dN + (OFF_T >> 4) + wg * 512), de = d128(dK + RING + (2 + wg) * 1024);
        mma_ss64<0, 1, 0>(ci, de, dt);
        mma_ss64<32, 1, 0>(ci, de + 512, dt);
        wg_commit();
        wg_wait<1>();
        freeT(3);
        fence_regs<0, 32>(ct);
#pragma unroll
        for (int k = 1; k < 4; k++) {
          mma_ss64<0, 1, 1>(ci, de + k * 2, dt + k * 128);
          mma_ss64<32, 1, 1>(ci, de + (512 + k * 2), dt + k * 128);
          if (k < 3) glu(IC<1>(), ct, 16, 48, 4 * k - 4, 4 * k);
        }
        wg_commit();
      }

      auto head = [&](auto off, int t, auto first) {
        constexpr int O = decltype(off)::value;
        mbar_wait(bars + 8 * (B_FT + (t & 3)), t >> 2);
        const uint64_t db = d128(dN + (t & 3) * (TB >> 4) + rank * 256);
        wg_fence();
        mma_rs64<O, 1, decltype(first)::value>(ct, h[0], h[1], h[2], h[3], db, zero);
#pragma unroll
        for (int k = 1; k < 6; k++) mma_rs64<O, 1, 1>(ct, h[4 * k], h[4 * k + 1], h[4 * k + 2], h[4 * k + 3], db + k * 128);
        wg_commit();
        wg_wait<1>();
      };
      auto rest = [&](auto off, int t) {
        constexpr int O = decltype(off)::value;
        const uint64_t db = d128(dN + (t & 3) * (TB >> 4)), dw = db + rank * 256, dm = db + (rank ? 0 : 1536);
        wg_fence();
#pragma unroll
        for (int k = 6; k < 12; k++) mma_rs64<O, 1, 1>(ct, h[4 * k], h[4 * k + 1], h[4 * k + 2], h[4 * k + 3], dw + k * 128);
#pragma unroll
        for (int k = 0; k < 2; k++) mma_rs64<O, 1, 1>(ct, h[48 + 4 * k], h[49 + 4 * k], h[50 + 4 * k], h[51 + 4 * k], dm + k * 128);
#pragma unroll
        for (int k = 0; k < 4; k++) mma_rs64<O, 1, 1>(ct, yf[4 * k], yf[4 * k + 1], yf[4 * k + 2], yf[4 * k + 3], db + (14 + k) * 128);
        wg_commit();
      };
      const uint32_t peerZ = mapa(sb + OFF_Z + tid * 16, rank ^ 1), peerB = mapa(bars + 8 * B_Z, rank ^ 1);
      auto send_peer = [&](auto off, int z) {
        constexpr int O = decltype(off)::value;
        fence_regs<O, 32>(ct);
#pragma unroll
        for (int i = 0; i < 4; i++)
          asm volatile("st.async.weak.shared::cluster.mbarrier::complete_tx::bytes.v4.b32 [%0], {%1,%2,%3,%4}, [%5];" ::"r"(peerZ + z * U + i * 4096),
                       "r"(pack_bf16(ct[O + 8 * i], ct[O + 8 * i + 1])), "r"(pack_bf16(ct[O + 8 * i + 2], ct[O + 8 * i + 3])),
                       "r"(pack_bf16(ct[O + 8 * i + 4], ct[O + 8 * i + 5])), "r"(pack_bf16(ct[O + 8 * i + 6], ct[O + 8 * i + 7])), "r"(peerB + 8 * z) : "memory");
      };
      auto send_grid = [&](auto off, int z) {
        constexpr int O = decltype(off)::value;
        fence_regs<O, 32>(ct);
        mbar_wait(bars + 8 * (B_Z + z), 0);
        uint4* dst = g_part + (size_t)((rb * 8 + 2 * ((q4 + z + 1) & 3) + rank) * 3 + z) * 1024 + tid;
#pragma unroll
        for (int i = 0; i < 4; i++) {
          const uint4 p = *(const uint4*)(smem + OFF_Z + z * U + i * 4096 + tid * 16);
          st_x4(dst + i * 256, (pack_bf16(ct[O + 8 * i] + bf_lo(p.x), ct[O + 8 * i + 1] + bf_hi(p.x)) & ~1u) | tag,
                pack_bf16(ct[O + 8 * i + 2] + bf_lo(p.y), ct[O + 8 * i + 3] + bf_hi(p.y)),
                pack_bf16(ct[O + 8 * i + 4] + bf_lo(p.z), ct[O + 8 * i + 5] + bf_hi(p.z)),
                pack_bf16(ct[O + 8 * i + 6] + bf_lo(p.w), ct[O + 8 * i + 7] + bf_hi(p.w)));
        }
        __syncwarp();
        if (lane == 0) hint_add(&g_cntP[32 * (rb * 8 + 2 * ((q4 + z + 1) & 3) + rank) + z]);
      };
      asm volatile("barrier.cluster.wait.aligned;" ::: "memory");
      head(IC<0>(), 0, IC<2>());
      if (elect) asm volatile("mbarrier.arrive.shared::cluster.b64 _, [%0];" ::"r"(mapa(bars + 8 * B_RDY, rank ^ 1)) : "memory");
      fence_regs<0, 64>(ci);
#pragma unroll
      for (int i = 0; i < 16; i++) {
        const float gg = ((i & 1) ? g1 : g0) * (2.0f / (2048.0f * 512.0f));
        if (i & 2) yf[i] = pack_pin((ci[2 * i] - ci[28 + 2 * i]) * gg, (ci[2 * i + 1] - ci[29 + 2 * i]) * gg);
        else yf[i] = pack_pin((ci[2 * i] + ci[36 + 2 * i]) * gg, (ci[2 * i + 1] + ci[37 + 2 * i]) * gg);
      }
      rest(IC<0>(), 0);
      if (tid == 0) PROF_EV(8);
      head(IC<32>(), 1, IC<HM>()); freeT(0); mbar_wait(bars + 8 * B_RDY, 0); send_peer(IC<0>(), 0); rest(IC<32>(), 1);
      head(IC<0>(), 2, IC<HM>()); freeT(1); send_peer(IC<32>(), 1); rest(IC<0>(), 2);
      head(IC<32>(), 3, IC<HM>()); freeT(2); send_peer(IC<0>(), 2); rest(IC<32>(), 3);
      head(IC<0>(), 4, IC<HM>()); freeT(3); send_grid(IC<32>(), 0); rest(IC<0>(), 4);
      head(IC<32>(), 5, IC<HM>()); send_grid(IC<0>(), 1); rest(IC<32>(), 5);
      head(IC<0>(), 6, IC<HM>()); send_grid(IC<32>(), 2); rest(IC<0>(), 6);
      head(IC<32>(), 7, IC<HM>()); send_peer(IC<0>(), 3);
      {
        const uint4* src = g_part + (size_t)(rb * 8 + j) * 3 * 1024 + tid;
        uint4 pv[12];
        mbar_wait(bars + 8 * (B_HP + 1), 0);
#pragma unroll
        for (int i = 0; i < 8; i++) pv[i] = ld_x4(src + i * 256);
        rest(IC<32>(), 7);
        if (tid == 0) PROF_EV(9);
        mbar_wait(bars + 8 * (B_HP + 2), 0);
        if (tid == 0) PROF_EV(24);
#pragma unroll
        for (int i = 8; i < 12; i++) pv[i] = ld_x4(src + i * 256);
        const uint32_t t0 = (uint32_t)clock();
        for (;;) {
          uint32_t bad = 0;
#pragma unroll
          for (int i = 0; i < 12; i++) bad |= pv[i].x ^ tag;
          if (!__any_sync(0xffffffffu, bad & 1)) break;
#pragma unroll
          for (int i = 0; i < 12; i++) pv[i] = ld_x4(src + i * 256);
          spin_guard(t0);
        }
        if (tid == 0) PROF_EV(14);
        float sum[32];
#pragma unroll
        for (int i = 0; i < 4; i++) {
          const uint32_t a[4] = {pv[i].x & ~1u, pv[i].y, pv[i].z, pv[i].w}, b[4] = {pv[4 + i].x & ~1u, pv[4 + i].y, pv[4 + i].z, pv[4 + i].w},
                         c[4] = {pv[8 + i].x & ~1u, pv[8 + i].y, pv[8 + i].z, pv[8 + i].w};
#pragma unroll
          for (int e = 0; e < 4; e++) {
            sum[8 * i + 2 * e] = bf_lo(a[e]) + bf_lo(b[e]) + bf_lo(c[e]);
            sum[8 * i + 2 * e + 1] = bf_hi(a[e]) + bf_hi(b[e]) + bf_hi(c[e]);
          }
        }
        mbar_wait(bars + 8 * (B_Z + 3), 0);
#pragma unroll
        for (int i = 0; i < 4; i++) {
          const uint4 p = *(const uint4*)(smem + OFF_Z + 3 * U + i * 4096 + tid * 16);
          const uint32_t a[4] = {p.x, p.y, p.z, p.w};
#pragma unroll
          for (int e = 0; e < 4; e++) { sum[8 * i + 2 * e] += bf_lo(a[e]); sum[8 * i + 2 * e + 1] += bf_hi(a[e]); }
        }
        wg_wait<0>();
        fence_regs<32, 32>(ct);
#pragma unroll
        for (int i = 0; i < 32; i++) sum[i] += ct[32 + i];
        const uint32_t stg = sb + OFF_T + warp * 2048;
        const int mr = (lane & 7) + ((lane >> 3) & 1) * 8, mc = lane >> 4;
#pragma unroll
        for (int i = 0; i < 4; i++) {
          const uint32_t a = stg + mr * 128 + (((2 * i + mc) ^ (mr & 7)) << 4);
          asm volatile("stmatrix.sync.aligned.m8n8.x4.shared.b16 [%0], {%1,%2,%3,%4};" ::"r"(a), "r"(pack_bf16(sum[8 * i], sum[8 * i + 1])),
                       "r"(pack_bf16(sum[8 * i + 2], sum[8 * i + 3])), "r"(pack_bf16(sum[8 * i + 4], sum[8 * i + 5])),
                       "r"(pack_bf16(sum[8 * i + 6], sum[8 * i + 7])) : "memory");
        }
        __syncwarp();
#pragma unroll
        for (int i = 0; i < 4; i++) {
          const int r = 4 * i + (lane >> 3), c = lane & 7;
          const uint4 v = *(const uint4*)(smem + OFF_T + warp * 2048 + r * 128 + ((c ^ (r & 7)) << 4));
          *(uint4*)(out + (size_t)(2 * rb + wg + 32 * (16 * w + r)) * 512 + 64 * j + 8 * c) = v;
        }
      }
      if (tid == 0) { g_epoch[blockIdx.x * 8] = ep + 1; PROF_EV(15); PROF_CK(41); }
    }
  } else if (warp < 12) {
    asm volatile("setmaxnreg.dec.sync.aligned.u32 104;");
    asm volatile("barrier.cluster.arrive.relaxed.aligned;" ::: "memory");
    const int t = tid - 256, w = warp - 8;
    const uint32_t ep = ld_x1(&g_epoch[blockIdx.x * 8]);
    const uint32_t tag = (ep + 1) & 1;
    auto gate_rows = [&] {
      uint4 xv[8], gv[2];
#pragma unroll
      for (int i = 0; i < 4; i++) {
        const int r = 16 * j + 4 * w + i;
        const uint4* p = (const uint4*)(x + (size_t)(2 * rb + (r >> 6) + 32 * (r & 63)) * 512) + lane;
        xv[2 * i] = __ldg(p); xv[2 * i + 1] = __ldg(p + 32);
      }
      gv[0] = __ldg((const uint4*)gate_w + lane); gv[1] = __ldg((const uint4*)gate_w + lane + 32);
      {
        float z[4];
#pragma unroll
        for (int i = 0; i < 4; i++) {
          float a = 0.f;
#pragma unroll
          for (int hh = 0; hh < 2; hh++) {
            const uint4 u = xv[2 * i + hh], v = gv[hh];
            a = fmaf(bf_lo(u.x), bf_lo(v.x), a); a = fmaf(bf_hi(u.x), bf_hi(v.x), a);
            a = fmaf(bf_lo(u.y), bf_lo(v.y), a); a = fmaf(bf_hi(u.y), bf_hi(v.y), a);
            a = fmaf(bf_lo(u.z), bf_lo(v.z), a); a = fmaf(bf_hi(u.z), bf_hi(v.z), a);
            a = fmaf(bf_lo(u.w), bf_lo(v.w), a); a = fmaf(bf_hi(u.w), bf_hi(v.w), a);
          }
#pragma unroll
          for (int o = 16; o; o >>= 1) a += __shfl_xor_sync(0xffffffffu, a, o);
          z[i] = a;
        }
        if (lane < 4) {
          const float zz = lane == 0 ? z[0] : lane == 1 ? z[1] : lane == 2 ? z[2] : z[3];
          asm volatile("st.relaxed.gpu.global.f32 [%0], %1;" ::"l"(g_gate + rb * 128 + 16 * j + 4 * w + lane), "f"(tagf(1.0f / (1.0f + __expf(-zz)), tag)) : "memory");
        }
        if (t == 0) PROF_EV(18);
      }
      if (w == 0) {
        const int c = lane >> 4, jj = 16 * blockIdx.x + (lane & 15), jm = (2048 - jj) & 2047;
        const unsigned short* pr = (const unsigned short*)w_r + 256 * c;
        const unsigned short* pi = (const unsigned short*)w_i + 256 * c;
        const float wr = 0.25f * (bf_lo(__ldg(pr + jj * 257)) + bf_lo(__ldg(pr + jm * 257)));
        const float wi = 0.25f * (bf_lo(__ldg(pi + jj * 257)) - bf_lo(__ldg(pi + jm * 257)));
        st_u2(g_Wh + c * 2048 + jj, c ? pack_bf16(-wi, wr) : pack_bf16(wr, wi), tag);
        __syncwarp();
        if (lane == 0) hint_add(&g_cntW[0]);
      }
    };
    {
      const int g = lane >> 2, q = lane & 3;
      uint32_t wf[32];
      if (!helper) {
        asm volatile("bar.sync 4, 256;" ::: "memory");
        mbar_wait(bars + 8 * (B_FX + GATE_AT), 0);
        gate_rows();
        const uint32_t wa = sb + OFF_T + w * (3072 + 4) + q * 48 + g * 2;
        mbar_wait(bars + 8 * B_C1, 0);
        if (t == 0) PROF_EV(32);
        __nanosleep(WPACE * w);
#pragma unroll
        for (int ri = 0; ri < 2; ri++) {
          if (lane == 0) {
            mbar_expect_tx(bars + 8 * (B_WR + w), 3072);
            tma4d(sb + OFF_T + w * 3072, ri ? &maps.wi : &maps.wr, bars + 8 * (B_WR + w), 16 * kg, 0, 2 * w, tn);
          }
          mbar_wait(bars + 8 * (B_WR + w), ri);
#pragma unroll
          for (int n2 = 0; n2 < 4; n2++) {
            uint32_t v[8];
#pragma unroll
            for (int i = 0; i < 8; i++)
              asm volatile("ld.shared.u16 %0, [%1];" : "=r"(v[i]) : "r"(wa + (2 * n2 + ((i >> 1) & 1)) * 192 + (i & 1) * (1536 + 2) + (i >> 2) * 16) : "memory");
#pragma unroll
            for (int i = 0; i < 8; i++) {
              uint32_t& d = wf[(i >> 2) * 16 + 4 * n2 + (i & 3)];
              d = ri ? d | (v[i] << 16) : v[i];
              asm volatile("" : "+r"(d)::"memory");
            }
          }
          __syncwarp();
        }
        asm volatile("bar.sync 1, 128;" ::: "memory");
        if (t == 0) PROF_EV(11);
      } else {
        asm volatile("bar.sync 4, 256;" ::: "memory");
        hint_wait(&g_cntW[0], (ep + 1) * 128u);
        const uint32_t t0 = (uint32_t)clock();
#pragma unroll 1
        for (;;) {
          uint32_t bad = 0;
#pragma unroll
          for (int i = 0; i < 32; i++) {
            const float2 v = ld_x2((const float2*)g_Wh + (i >> 4) * 2048 + 16 * w + g + 8 * (i & 1) + 64 * q + ((i >> 1) & 7) * 256);
            wf[i] = __float_as_uint(v.x); bad |= __float_as_uint(v.y) ^ tag;
          }
          if (!__any_sync(0xffffffffu, bad & 1)) break;
          spin_guard(t0);
        }
        if (t == 0) PROF_EV(11);
      }
      if (t == 0) { mbar_expect_tx(bars + 8 * B_W, 8192); bulk_load(sb + OFF_D, g_DT.v, 8192, bars + 8 * B_W); }
      mbar_wait(bars + 8 * B_W, 0);
      mbar_wait(bars + 8 * B_HX, 0);
      if (t == 0) PROF_EV(12);
      const uint32_t dd = (sb & 0x3FFFF) >> 4;
      const uint64_t dF = d128((dd + (OFF_D >> 4)) | (512u << 16)), dI = d128((dd + (OFF_D >> 4)) | (1u << 16)), dA = d128((dd + (OFF_XB >> 4)) | (512u << 16));
      float az[32];
      const int zero = blockIdx.x >> 16;
      uint32_t pf[32];
#pragma unroll
      for (int mt = 0; mt < 2; mt++) {
        wg_fence();
        if (mt == 0) mma_ss64<0, 3, 0>(az, dA, dF);
        else mma_ss64<0, 3, 2>(az, dA + 512, dF, zero);
#pragma unroll
        for (int k = 1; k < 4; k++) mma_ss64<0, 3, 1>(az, dA + (mt * 512 + k * 128), dF + k * 128);
        wg_commit();
        wg_wait<0>();
        fence_regs<0, 32>(az);
#pragma unroll
        for (int i = 0; i < 16; i++) {
          const float wr = bf_lo(wf[16 * mt + i]), wi = bf_hi(wf[16 * mt + i]);
          pf[16 * mt + i] = pack_pin(fmaf(az[2 * i], wr, -az[2 * i + 1] * wi), fmaf(az[2 * i], wi, az[2 * i + 1] * wr));
        }
      }
      if (t == 0) PROF_EV(16);
#pragma unroll
      for (int mt = 0; mt < 2; mt++) {
        wg_fence();
        mma_rs64<0, 0, 2>(az, pf[16 * mt], pf[16 * mt + 1], pf[16 * mt + 2], pf[16 * mt + 3], dI, mt ? (int)helper : zero);
#pragma unroll
        for (int k = 1; k < 4; k++) mma_rs64<0, 0, 1>(az, pf[16 * mt + 4 * k], pf[16 * mt + 4 * k + 1], pf[16 * mt + 4 * k + 2], pf[16 * mt + 4 * k + 3], dI + k * 2);
        wg_commit();
        wg_wait<0>();
        fence_regs<0, 32>(az);
        if (!helper) {
          const int m = lane >> 3, r = lane & 7;
          const int sl = 2 * (m >> 1) + ((r >> 1) & 1) + 4 * (r >> 2);
          const uint32_t a0 = sb + OFF_XB + (2 * w + (m & 1)) * 2048 + sl * 64 + (((mt * 2 + (r & 1)) ^ (sl >> 1)) << 4);
#pragma unroll
          for (int i = 0; i < 4; i++)
            stsm4t(a0 + i * 512, pack_bf16(az[8 * i], az[8 * i + 1]), pack_bf16(az[8 * i + 2], az[8 * i + 3]), pack_bf16(az[8 * i + 4], az[8 * i + 5]),
                   pack_bf16(az[8 * i + 6], az[8 * i + 7]));
        }
      }
      if (helper) {
#pragma unroll
        for (int i = 0; i < 16; i++) {
          const int n = i >> 1, s0 = 8 * (n >> 1) + 2 * (n & 1) + (q & 1) + 4 * (q >> 1);
          if ((n & 1) == (int)(blockIdx.x & 1)) st_u2(g_Ts + s0 * 64 + 16 * w + g + 8 * (i & 1), pack_bf16(az[2 * i], az[2 * i + 1]), tag);
        }
        __syncwarp();
        if (lane == 0) hint_add(&g_cntH[0]);
        if (t == 0) { g_epoch[blockIdx.x * 8] = ep + 1; PROF_EV(13); }
      } else {
        asm volatile("fence.proxy.async.shared::cta;" ::: "memory");
        __syncwarp();
        if (lane == 0) {
          if (t == 0) PROF_EV(17);
          if (SPACE) __nanosleep(SPACE * w);
          asm volatile("cp.async.bulk.tensor.3d.global.shared::cta.bulk_group [%0, {%2, %3, %4}], [%1];" ::"l"(&maps.ts), "r"(sb + OFF_XB + w * 4096),
                       "r"(32 * kg), "r"(0), "r"(8 * tn + 2 * w) : "memory");
          bulk_done_signal(&g_cntT[32 * j]);
          if (t == 96) PROF_EV(13);
        }
        __syncwarp();
        if (j == 0) {
          hint_wait(&g_cntH[0], (ep + 1) * 8u);
          const uint32_t t0 = (uint32_t)clock();
          float2 v;
          do { v = ld_x2((const float2*)g_Ts + 2 * rb * 64 + t); spin_guard(t0); } while (__any_sync(0xffffffffu, (__float_as_uint(v.y) ^ tag) & 1));
          mbar_wait(bars + 8 * B_TL, 0);
          const uint32_t u = __float_as_uint(v.x);
          *(uint16_t*)(smem + OFF_T + t * 128 + ((t & 7) << 4)) = (uint16_t)u;
          *(uint16_t*)(smem + OFF_T + t * 128 + (((t & 7) ^ 1) << 4)) = (uint16_t)(u >> 16);
          asm volatile("fence.proxy.async.shared::cta;" ::: "memory");
          __syncwarp();
          if (lane == 0) mbar_arrive(bars + 8 * B_T);
        }
      }
    }
  } else {
    asm volatile("setmaxnreg.dec.sync.aligned.u32 24;");
    if (warp < 14) {
      if (lane == 0) {
#pragma unroll
        for (int i = 0; i < 6; i++) mbar_init(bars + 8 * (2 * i + warp - 12), 1);
        asm volatile("fence.proxy.async.shared::cta;" ::: "memory");
      }
      asm volatile("bar.sync 2, 64;" ::: "memory");
      asm volatile("bar.arrive 0, 384;" ::: "memory");
      asm volatile("bar.arrive 4, 256;" ::: "memory");
      if (lane == 0) {
        if (!helper) {
#pragma unroll 1
          for (int n = 0; n < NR; n++) { if (warp == 12) x_load(n); ring_part(warp - 12, n, n); }
        }
      }
    } else {
      if (lane != 0) {
      } else if (warp == 15) {
#pragma unroll
        for (int i = B_FT; i < NBAR; i++) mbar_init(bars + 8 * i, i < B_EA ? 1 : i < B_T ? 2 : 4);
#pragma unroll
        for (int i = 0; i < 4; i++) mbar_expect_tx(bars + 8 * (B_Z + i), U);
        asm volatile("fence.mbarrier_init.release.cluster;" ::: "memory");
        asm volatile("fence.proxy.async.shared::cta;" ::: "memory");
      } else {
#pragma unroll
        for (int i = 1; i < 4; i++) asm volatile("prefetch.tensormap [%0];" ::"l"((const char*)&maps + i * 128) : "memory");
      }
      if (lane == 0) PROF_EV(warp + 14);
      __syncwarp();
      asm volatile("bar.arrive 0, 384;" ::: "memory");
      asm volatile("bar.arrive 4, 256;" ::: "memory");
    }
    __syncwarp();
    asm volatile("barrier.cluster.arrive.relaxed.aligned;" ::: "memory");
    asm volatile("bar.sync 3, 128;" ::: "memory");
    if (lane == 0 && (!helper || warp == 15)) {
      if (warp < 14) {
        if (warp == 12) x_load(NR);
        int slot = 0, par = 0;
#pragma unroll 1
        for (int n = NR; n < 32; n++) {
          mbar_wait(bars + 8 * (B_EA + slot), par);
          ring_part(warp - 12, n, slot);
          if (warp == 12 && n < 7) x_load(n + 1);
          if (++slot == NR) { slot = 0; par ^= 1; }
        }
      } else if (warp == 15) {
        const unsigned ep1 = ld_x1(&g_epoch[blockIdx.x * 8]) + 1;
        flag_wait(&g_cntX[helper ? 0 : 32 * j], ep1 * 16u);
        PROF_EV(22);
        mbar_expect_tx(bars + 8 * B_HX, U);
        bulk_load(sb + OFF_XB, g_X + (size_t)(helper ? 128 : kg * 8 + tn) * 8192, U, bars + 8 * B_HX);
        if (!helper) {
          flag_wait(&g_cntT[32 * j], ep1 * 64u);
          PROF_EV(23);
          mbar_expect_tx(bars + 8 * B_TL, U);
          tma3d(sb + OFF_T, &maps.t, bars + 8 * B_TL, 64 * j, 0, 2 * rb);
#pragma unroll 1
          for (int i = 0; i < 3; i++) { hint_wait(&g_cntP[32 * (rb * 8 + j) + i], ep1 * 8u); mbar_arrive(bars + 8 * (B_HP + i)); }
        }
      } else {
#pragma unroll 1
        for (int h2 = 0; h2 < 2; h2++) {
          const int s0 = 2 * rb + h2, sg = (s0 & ~6) | ((s0 & 2) << 1) | ((s0 & 4) >> 1);
          mbar_wait(bars + 8 * (B_XS + h2), 0);
#pragma unroll 1
          for (int c = 0; c < 2; c++) {
            asm volatile("cp.async.bulk.tensor.4d.global.shared::cta.bulk_group [%0, {%2, %3, %4, %5}], [%1];" ::"l"(&maps.xs),
                         "r"(sb + OFF_XB + h2 * 8192 + c * 4096), "r"(0), "r"(sg), "r"(0), "r"(16 * j + 8 * c) : "memory");
            if (j == 0)
              asm volatile("cp.async.bulk.global.shared::cta.bulk_group [%0], [%1], 256;" ::"l"(g_X + 128 * 8192 + c * 4096 + sg * 128),
                           "r"(sb + OFF_SP + h2 * 512 + c * 256) : "memory");
            if (SPACE && h2 + c < 2) __nanosleep(SPACE);
          }
        }
        bulk_done_signal(&g_cntX[32 * j]);
        PROF_EV(20);
#pragma unroll 1
        for (int t = 0; t < 8; t++) {
          const int i = t < 3 ? t + 1 : t < 6 ? t - 2 : 0;
          const int col = 64 * (2 * ((q4 + i) & 3) + ((t < 3 || t == 6) ? 1 - rank : rank));
          const uint32_t fb = bars + 8 * (B_FT + (t & 3)), dst = sb + (t & 3) * TB;
          mbar_wait(bars + 8 * (B_ET + (t == 2 ? 3 : t & 3)), t >> 2);
          mbar_expect_tx(fb, TB);
          tma2d(dst, &maps.d224, fb, col, 224 * j);
          if (t < 2) mbar_wait(bars + 8 * (B_ET + t + 1), 0);
          tma2d(dst + 28672, &maps.ft, fb, col, 64 * j);
        }
      }
    }
  }
}

typedef CUresult (*EncodeFn)(CUtensorMap*, CUtensorMapDataType, cuuint32_t, void*, const cuuint64_t*, const cuuint64_t*, const cuuint32_t*,
                             const cuuint32_t*, CUtensorMapInterleave, CUtensorMapSwizzle, CUtensorMapL2promotion, CUtensorMapFloatOOBfill);

static void encode(EncodeFn f, CUtensorMap* m, const void* base, int rank, const cuuint64_t* dims, const cuuint64_t* strides, const cuuint32_t* box,
                   CUtensorMapSwizzle sw) {
  cuuint32_t es[5] = {1, 1, 1, 1, 1};
  f(m, CU_TENSOR_MAP_DATA_TYPE_BFLOAT16, rank, (void*)base, dims, strides, box, es, CU_TENSOR_MAP_INTERLEAVE_NONE, sw,
    CU_TENSOR_MAP_L2_PROMOTION_L2_128B, CU_TENSOR_MAP_FLOAT_OOB_FILL_NONE);
}

extern "C" void kernel_launch(void* const* d_in, const int* in_sizes, int n_in, void* d_out, int out_size) {
  (void)in_sizes; (void)n_in; (void)out_size;
  const __nv_bfloat16* x = (const __nv_bfloat16*)d_in[0];
  const __nv_bfloat16* w_r = (const __nv_bfloat16*)d_in[1];
  const __nv_bfloat16* w_i = (const __nv_bfloat16*)d_in[2];
  const __nv_bfloat16* Wg = (const __nv_bfloat16*)d_in[4];
  const __nv_bfloat16* Wu = (const __nv_bfloat16*)d_in[5];
  const __nv_bfloat16* Wd = (const __nv_bfloat16*)d_in[6];
  const __nv_bfloat16* gw = (const __nv_bfloat16*)d_in[7];

  void* fp = nullptr; cudaDriverEntryPointQueryResult qr;
  cudaGetDriverEntryPoint("cuTensorMapEncodeTiled", &fp, cudaEnableDefault, &qr);
  EncodeFn enc = (EncodeFn)fp;
  void *pFT, *pET, *pX, *pT;
  cudaGetSymbolAddress(&pX, g_X); cudaGetSymbolAddress(&pT, g_T);
  cudaGetSymbolAddress(&pFT, g_FT); cudaGetSymbolAddress(&pET, g_ET);

  Maps mp;
  const CUtensorMapSwizzle S128 = CU_TENSOR_MAP_SWIZZLE_128B, S64 = CU_TENSOR_MAP_SWIZZLE_64B;
  { cuuint64_t d[3] = {512, 64, 32}, s[2] = {32768, 1024}; cuuint32_t b[3] = {64, 64, 2}; encode(enc, &mp.x, x, 3, d, s, b, S128); }
  { cuuint64_t d[2] = {512, 512}, s[1] = {1024}; cuuint32_t b[2] = {64, 64}; encode(enc, &mp.ft, pFT, 2, d, s, b, S128); }
  { cuuint64_t d[4] = {128, 32, 2, 129}, s[3] = {256, 8192, 16384}; cuuint32_t b[4] = {128, 1, 2, 8}; encode(enc, &mp.xs, pX, 4, d, s, b, CU_TENSOR_MAP_SWIZZLE_NONE); }
  { cuuint64_t d[3] = {512, 32, 64}, s[2] = {65536, 1024}; cuuint32_t b[3] = {32, 32, 2}; encode(enc, &mp.ts, pT, 3, d, s, b, S64); }
  { cuuint64_t d[3] = {512, 64, 32}, s[2] = {1024, 65536}; cuuint32_t b[3] = {64, 64, 2}; encode(enc, &mp.t, pT, 3, d, s, b, S128); }
  { cuuint64_t d[4] = {64, 64, 2, 32}, s[3] = {8192, 128, 256}; cuuint32_t b[4] = {64, 64, 2, 1}; encode(enc, &mp.e, pET, 4, d, s, b, S128); }
  { cuuint64_t d[2] = {1792, 512}, s[1] = {3584}; cuuint32_t b[2] = {64, 64}, b2[2] = {32, 128};
    encode(enc, &mp.g64, Wg, 2, d, s, b, S128); encode(enc, &mp.u64, Wu, 2, d, s, b, S128);
    encode(enc, &mp.g32, Wg, 2, d, s, b2, S64); encode(enc, &mp.u32, Wu, 2, d, s, b2, S64); }
  { cuuint64_t d[2] = {512, 1792}, s[1] = {1024}; cuuint32_t b[2] = {64, 224}; encode(enc, &mp.d224, Wd, 2, d, s, b, S128); }
  { cuuint64_t d[4] = {264, 32, 8, 8}, s[3] = {32896, 512, 4112}; cuuint32_t b[4] = {24, 32, 2, 1};
    encode(enc, &mp.wr, w_r, 4, d, s, b, CU_TENSOR_MAP_SWIZZLE_NONE); encode(enc, &mp.wi, w_i, 4, d, s, b, CU_TENSOR_MAP_SWIZZLE_NONE); }

  cudaFuncSetAttribute(fused_kernel, cudaFuncAttributeMaxDynamicSharedMemorySize, SMEM_BYTES);
  fused_kernel<<<NCTA, 512, SMEM_BYTES>>>(mp, x, w_r, w_i, gw, (__nv_bfloat16*)d_out);
}
```

```cpp
#include <cuda_runtime.h>
#include <cuda_bf16.h>
#include <cuda.h>
#include <stdint.h>

namespace tbl {
constexpr double PI = 3.14159265358979323846264338327950288;
constexpr double sin_s(double x) { double t = x, s = x; for (int n = 1; n < 12; n++) { t *= -x * x / ((2 * n) * (2 * n + 1)); s += t; } return s; }
constexpr double cos_s(double x) { double t = 1, s = 1; for (int n = 1; n < 12; n++) { t *= -x * x / ((2 * n - 1) * (2 * n)); s += t; } return s; }
constexpr double cos2048(int m) {
  m &= 2047; if (m > 1024) m = 2048 - m;
  bool neg = false; if (m > 512) { m = 1024 - m; neg = true; }
  double v = (m <= 256) ? cos_s(2 * PI * m / 2048) : sin_s(2 * PI * (512 - m) / 2048);
  return neg ? -v : v;
}
constexpr uint16_t to_bf16(double v) {
  if (v == 0) return 0;
  uint16_t s = 0; if (v < 0) { s = 0x8000; v = -v; }
  int e = 0; while (v >= 2) { v /= 2; e++; } while (v < 1) { v *= 2; e--; }
  double m = (v - 1) * 128; int mi = (int)m; double fr = m - mi;
  if (fr > 0.5 || (fr == 0.5 && (mi & 1))) mi++;
  if (mi == 128) { mi = 0; e++; }
  return (uint16_t)(s | ((e + 127) << 7) | mi);
}
struct CosT { uint16_t v[2048]; constexpr CosT() : v() { for (int i = 0; i < 2048; i++) v[i] = to_bf16(cos2048(i)); } };
struct alignas(1024) FT {
  uint16_t v[512 * 512];
  constexpr FT() : v() {
    CosT c;
    for (int r = 0; r < 512; r++) {
      int k = (r >> 4) * 8 + (r & 7), e = (r >> 3) & 1;
      int mul = 4 * k, add = e ? 512 : 0;
      if (k == 0 && e == 1) { mul = 1024; add = 0; }
      for (int d = 0; d < 512; d++) v[r * 512 + d] = c.v[(d * mul + add) & 2047];
    }
  }
};
struct alignas(1024) ET {
  uint16_t v[2048 * 128];
  constexpr ET() : v() {
    CosT c;
    for (int s = 0; s < 2048; s++)
      for (int j = 0; j < 64; j++) { v[s * 128 + j] = c.v[(s * j) & 2047]; v[s * 128 + 64 + j] = c.v[(s * j + 512) & 2047]; }
  }
};
struct alignas(1024) DT {
  uint16_t v[64 * 64];
  constexpr DT() : v() {
    CosT c;
    for (int r = 0; r < 64; r++)
      for (int n = 0; n < 64; n++) {
        const int sg = r >> 1, s0 = (sg & ~6) | ((sg & 2) << 1) | ((sg & 4) >> 1), e = r & 1, f = n & 1;
        const int m = 64 * s0 * (n >> 1) + (e == f ? 0 : e ? -512 : 512);
        v[r * 64 + (((n >> 3) ^ (r & 7)) << 3) + (n & 7)] = c.v[m & 2047];
      }
  }
};
}

__device__ constexpr tbl::FT g_FT = tbl::FT();
__device__ constexpr tbl::ET g_ET = tbl::ET();
__device__ constexpr tbl::DT g_DT = tbl::DT();

__device__ __align__(1024) uint16_t g_X[129 * 8192];
__device__ __align__(1024) uint16_t g_T[32 * 64 * 512];
__device__ __align__(1024) uint2 g_Ts[32 * 64];
__device__ __align__(1024) uint4 g_part[128 * 3 * 1024];
__device__ __align__(16) float g_gate[16 * 128];
__device__ __align__(16) uint2 g_Wh[2 * 2048];
__device__ unsigned g_epoch[132 * 8];
__device__ unsigned g_cntX[8 * 32], g_cntT[8 * 32], g_cntP[128 * 32], g_cntW[32], g_cntH[32];
#define PROF_EV(i) do {} while (0)
#define PROF_CK(i) do {} while (0)

__device__ __forceinline__ uint32_t smem_u32(const void* p) { return (uint32_t)__cvta_generic_to_shared(p); }
__device__ __forceinline__ void mbar_init(uint32_t bar, uint32_t cnt) { asm volatile("mbarrier.init.shared::cta.b64 [%0], %1;" ::"r"(bar), "r"(cnt)); }
__device__ __forceinline__ void mbar_expect_tx(uint32_t bar, uint32_t bytes) { asm volatile("mbarrier.arrive.expect_tx.shared::cta.b64 _, [%0], %1;" ::"r"(bar), "r"(bytes) : "memory"); }
__device__ __forceinline__ void mbar_arrive(uint32_t bar) { asm volatile("mbarrier.arrive.shared::cta.b64 _, [%0];" ::"r"(bar) : "memory"); }
__device__ __forceinline__ void mbar_wait(uint32_t bar, uint32_t parity) {
  asm volatile(
      "{\n.reg .pred p;\n.reg .u32 n;\nmov.u32 n, 0;\n"
      "W_LOOP:\nmbarrier.try_wait.parity.shared::cta.b64 p, [%0], %1;\n@p bra W_DONE;\n"
      "add.u32 n, n, 1;\nsetp.lt.u32 p, n, 0x40000;\n@p bra W_LOOP;\ntrap;\nW_DONE:\n}" ::"r"(bar), "r"(parity) : "memory");
}
__device__ __forceinline__ void bulk_load(uint32_t dst, const void* src, uint32_t bytes, uint32_t bar) {
  asm volatile("cp.async.bulk.shared::cluster.global.mbarrier::complete_tx::bytes [%0], [%1], %2, [%3];" ::"r"(dst), "l"(src), "r"(bytes), "r"(bar) : "memory");
}
__device__ __forceinline__ void cp16(uint32_t dst, const void* src) { asm volatile("cp.async.cg.shared.global [%0], [%1], 16;" ::"r"(dst), "l"(src) : "memory"); }
__device__ __forceinline__ void spin_guard(uint32_t t0) { if ((uint32_t)clock() - t0 > (1u << 30)) __trap(); }
__device__ __forceinline__ float tagf(float v, uint32_t tag) { return __uint_as_float((__float_as_uint(v) & ~1u) | tag); }
__device__ __forceinline__ float untag(float v) { return __uint_as_float(__float_as_uint(v) & ~1u); }
__device__ __forceinline__ void st_x2(float2* p, float a, float b) { asm volatile("st.relaxed.gpu.global.v2.f32 [%0], {%1,%2};" ::"l"(p), "f"(a), "f"(b) : "memory"); }
__device__ __forceinline__ float2 ld_x2(const float2* p) { float2 v; asm volatile("ld.relaxed.gpu.global.v2.f32 {%0,%1}, [%2];" : "=f"(v.x), "=f"(v.y) : "l"(p) : "memory"); return v; }
__device__ __forceinline__ void st_u2(uint2* p, uint32_t a, uint32_t b) { asm volatile("st.relaxed.gpu.global.v2.u32 [%0], {%1,%2};" ::"l"(p), "r"(a), "r"(b) : "memory"); }
__device__ __forceinline__ void prefetch2d(const CUtensorMap* m, int c0, int c1) { asm volatile("cp.async.bulk.prefetch.tensor.2d.L2.global [%0, {%1, %2}];" ::"l"(m), "r"(c0), "r"(c1) : "memory"); }
__device__ __forceinline__ void prefetch1d(const void* p, uint32_t bytes) { asm volatile("cp.async.bulk.prefetch.L2.global [%0], %1;" ::"l"(p), "r"(bytes) : "memory"); }
__device__ __forceinline__ uint32_t ld_x1(const void* p) { uint32_t v; asm volatile("ld.relaxed.gpu.global.u32 %0, [%1];" : "=r"(v) : "l"(p) : "memory"); return v; }
__device__ __forceinline__ uint4 ld_x4(const void* p) { uint4 v; asm volatile("ld.relaxed.gpu.global.v4.u32 {%0,%1,%2,%3}, [%4];" : "=r"(v.x), "=r"(v.y), "=r"(v.z), "=r"(v.w) : "l"(p) : "memory"); return v; }
__device__ __forceinline__ void st_x4(void* p, uint32_t a, uint32_t b, uint32_t c, uint32_t d) { asm volatile("st.relaxed.gpu.global.v4.u32 [%0], {%1,%2,%3,%4};" ::"l"(p), "r"(a), "r"(b), "r"(c), "r"(d) : "memory"); }
__device__ __forceinline__ uint32_t mapa(uint32_t a, uint32_t cta) { uint32_t r; asm volatile("mapa.shared::cluster.u32 %0, %1, %2;" : "=r"(r) : "r"(a), "r"(cta)); return r; }
__device__ __forceinline__ void stsm4t(uint32_t a, uint32_t r0, uint32_t r1, uint32_t r2, uint32_t r3) {
  asm volatile("stmatrix.sync.aligned.m8n8.x4.trans.shared.b16 [%0], {%1,%2,%3,%4};" ::"r"(a), "r"(r0), "r"(r1), "r"(r2), "r"(r3) : "memory");
}
__device__ __forceinline__ void hint_add(unsigned* p) { asm volatile("red.relaxed.gpu.global.add.u32 [%0], 1;" ::"l"(p) : "memory"); }
__device__ __forceinline__ void hint_wait(const unsigned* p, unsigned target) {
  const uint32_t t0 = (uint32_t)clock();
  while ((int)(ld_x1(p) - target) < 0) spin_guard(t0);
}
__device__ __forceinline__ void bulk_done_signal(unsigned* p) {
  asm volatile("cp.async.bulk.commit_group;\ncp.async.bulk.wait_group 0;\nfence.proxy.async.global;" ::: "memory");
  hint_add(p);
}
__device__ __forceinline__ void flag_wait(const unsigned* p, unsigned target) {
  hint_wait(p, target);
  asm volatile("fence.proxy.async.global;" ::: "memory");
}
__device__ __forceinline__ void tma2d(uint32_t dst, const CUtensorMap* m, uint32_t bar, int c0, int c1) {
  asm volatile("cp.async.bulk.tensor.2d.shared::cluster.global.mbarrier::complete_tx::bytes [%0], [%1, {%3, %4}], [%2];" ::"r"(dst), "l"(m), "r"(bar), "r"(c0), "r"(c1) : "memory");
}
__device__ __forceinline__ void tma3d(uint32_t dst, const CUtensorMap* m, uint32_t bar, int c0, int c1, int c2) {
  asm volatile("cp.async.bulk.tensor.3d.shared::cluster.global.mbarrier::complete_tx::bytes [%0], [%1, {%3, %4, %5}], [%2];" ::"r"(dst), "l"(m), "r"(bar), "r"(c0), "r"(c1), "r"(c2) : "memory");
}
__device__ __forceinline__ void tma4d(uint32_t dst, const CUtensorMap* m, uint32_t bar, int c0, int c1, int c2, int c3) {
  asm volatile("cp.async.bulk.tensor.4d.shared::cluster.global.mbarrier::complete_tx::bytes [%0], [%1, {%3, %4, %5, %6}], [%2];" ::"r"(dst), "l"(m), "r"(bar), "r"(c0), "r"(c1), "r"(c2), "r"(c3) : "memory");
}
__device__ __forceinline__ void wg_fence() { asm volatile("wgmma.fence.sync.aligned;" ::: "memory"); }
__device__ __forceinline__ void wg_commit() { asm volatile("wgmma.commit_group.sync.aligned;" ::: "memory"); }
template <int N> __device__ __forceinline__ void wg_wait() { asm volatile("wgmma.wait_group.sync.aligned %0;" ::"n"(N) : "memory"); }
template <int O, int N, int NN> __device__ __forceinline__ void fence_regs(float (&d)[NN]) {
#pragma unroll
  for (int i = 0; i < N; i++) asm volatile("" : "+f"(d[O + i])::"memory");
}
__device__ __forceinline__ uint32_t pack_bf16(float lo, float hi) {
  uint32_t r; asm("cvt.rn.bf16x2.f32 %0, %1, %2;" : "=r"(r) : "f"(hi), "f"(lo)); return r;
}
__device__ __forceinline__ uint32_t pack_pin(float lo, float hi) {
  uint32_t r; asm volatile("cvt.rn.bf16x2.f32 %0, %1, %2;" : "=r"(r) : "f"(hi), "f"(lo) : "memory"); return r;
}
__device__ __forceinline__ float bf_lo(uint32_t u) { return __uint_as_float(u << 16); }
__device__ __forceinline__ float bf_hi(uint32_t u) { return __uint_as_float(u & 0xffff0000u); }

__device__ __forceinline__ uint64_t d128(uint32_t lo) { uint64_t d; asm("mov.b64 %0, {%1, 0x40000040};" : "=l"(d) : "r"(lo)); return d; }
__device__ __forceinline__ uint64_t d64(uint32_t lo) { uint64_t d; asm("mov.b64 %0, {%1, 0x80000020};" : "=l"(d) : "r"(lo)); return d; }
template<int O,int TB,int ACC,int NN> __device__ __forceinline__ void mma_ss64(float (&d)[NN], uint64_t da, uint64_t db, int sd = 0){
  if constexpr (ACC == 1) asm volatile("wgmma.mma_async.sync.aligned.m64n64k16.f32.bf16.bf16 {%0,%1,%2,%3,%4,%5,%6,%7,%8,%9,%10,%11,%12,%13,%14,%15,%16,%17,%18,%19,%20,%21,%22,%23,%24,%25,%26,%27,%28,%29,%30,%31}, %32, %33, 1, 1, 1, %35, %34;"
   : "+f"(d[O+0]), "+f"(d[O+1]), "+f"(d[O+2]), "+f"(d[O+3]), "+f"(d[O+4]), "+f"(d[O+5]), "+f"(d[O+6]), "+f"(d[O+7]), "+f"(d[O+8]), "+f"(d[O+9]), "+f"(d[O+10]), "+f"(d[O+11]), "+f"(d[O+12]), "+f"(d[O+13]), "+f"(d[O+14]), "+f"(d[O+15]), "+f"(d[O+16]), "+f"(d[O+17]), "+f"(d[O+18]), "+f"(d[O+19]), "+f"(d[O+20]), "+f"(d[O+21]), "+f"(d[O+22]), "+f"(d[O+23]), "+f"(d[O+24]), "+f"(d[O+25]), "+f"(d[O+26]), "+f"(d[O+27]), "+f"(d[O+28]), "+f"(d[O+29]), "+f"(d[O+30]), "+f"(d[O+31])
   : "l"(da), "l"(db), "n"(TB & 1), "n"(TB >> 1));
  else if constexpr (ACC == 0) asm volatile("wgmma.mma_async.sync.aligned.m64n64k16.f32.bf16.bf16 {%0,%1,%2,%3,%4,%5,%6,%7,%8,%9,%10,%11,%12,%13,%14,%15,%16,%17,%18,%19,%20,%21,%22,%23,%24,%25,%26,%27,%28,%29,%30,%31}, %32, %33, 0, 1, 1, %35, %34;"
   : "=f"(d[O+0]), "=f"(d[O+1]), "=f"(d[O+2]), "=f"(d[O+3]), "=f"(d[O+4]), "=f"(d[O+5]), "=f"(d[O+6]), "=f"(d[O+7]), "=f"(d[O+8]), "=f"(d[O+9]), "=f"(d[O+10]), "=f"(d[O+11]), "=f"(d[O+12]), "=f"(d[O+13]), "=f"(d[O+14]), "=f"(d[O+15]), "=f"(d[O+16]), "=f"(d[O+17]), "=f"(d[O+18]), "=f"(d[O+19]), "=f"(d[O+20]), "=f"(d[O+21]), "=f"(d[O+22]), "=f"(d[O+23]), "=f"(d[O+24]), "=f"(d[O+25]), "=f"(d[O+26]), "=f"(d[O+27]), "=f"(d[O+28]), "=f"(d[O+29]), "=f"(d[O+30]), "=f"(d[O+31])
   : "l"(da), "l"(db), "n"(TB & 1), "n"(TB >> 1));
  else asm volatile("{\n.reg .pred p;\nsetp.ne.b32 p, %36, 0;\nwgmma.mma_async.sync.aligned.m64n64k16.f32.bf16.bf16 {%0,%1,%2,%3,%4,%5,%6,%7,%8,%9,%10,%11,%12,%13,%14,%15,%16,%17,%18,%19,%20,%21,%22,%23,%24,%25,%26,%27,%28,%29,%30,%31}, %32, %33, p, 1, 1, %35, %34;\n}"
   : "+f"(d[O+0]), "+f"(d[O+1]), "+f"(d[O+2]), "+f"(d[O+3]), "+f"(d[O+4]), "+f"(d[O+5]), "+f"(d[O+6]), "+f"(d[O+7]), "+f"(d[O+8]), "+f"(d[O+9]), "+f"(d[O+10]), "+f"(d[O+11]), "+f"(d[O+12]), "+f"(d[O+13]), "+f"(d[O+14]), "+f"(d[O+15]), "+f"(d[O+16]), "+f"(d[O+17]), "+f"(d[O+18]), "+f"(d[O+19]), "+f"(d[O+20]), "+f"(d[O+21]), "+f"(d[O+22]), "+f"(d[O+23]), "+f"(d[O+24]), "+f"(d[O+25]), "+f"(d[O+26]), "+f"(d[O+27]), "+f"(d[O+28]), "+f"(d[O+29]), "+f"(d[O+30]), "+f"(d[O+31])
   : "l"(da), "l"(db), "n"(TB & 1), "n"(TB >> 1), "r"(sd));
}
template<int O,int TB,int ACC,int NN> __device__ __forceinline__ void mma_rs64(float (&d)[NN], uint32_t a0, uint32_t a1, uint32_t a2, uint32_t a3, uint64_t db, int sd = 0){
  if constexpr (ACC == 1) asm volatile("wgmma.mma_async.sync.aligned.m64n64k16.f32.bf16.bf16 {%0,%1,%2,%3,%4,%5,%6,%7,%8,%9,%10,%11,%12,%13,%14,%15,%16,%17,%18,%19,%20,%21,%22,%23,%24,%25,%26,%27,%28,%29,%30,%31}, {%32,%33,%34,%35}, %36, 1, 1, 1, %37;"
   : "+f"(d[O+0]), "+f"(d[O+1]), "+f"(d[O+2]), "+f"(d[O+3]), "+f"(d[O+4]), "+f"(d[O+5]), "+f"(d[O+6]), "+f"(d[O+7]), "+f"(d[O+8]), "+f"(d[O+9]), "+f"(d[O+10]), "+f"(d[O+11]), "+f"(d[O+12]), "+f"(d[O+13]), "+f"(d[O+14]), "+f"(d[O+15]), "+f"(d[O+16]), "+f"(d[O+17]), "+f"(d[O+18]), "+f"(d[O+19]), "+f"(d[O+20]), "+f"(d[O+21]), "+f"(d[O+22]), "+f"(d[O+23]), "+f"(d[O+24]), "+f"(d[O+25]), "+f"(d[O+26]), "+f"(d[O+27]), "+f"(d[O+28]), "+f"(d[O+29]), "+f"(d[O+30]), "+f"(d[O+31])
   : "r"(a0), "r"(a1), "r"(a2), "r"(a3), "l"(db), "n"(TB));
  else if constexpr (ACC == 0) asm volatile("wgmma.mma_async.sync.aligned.m64n64k16.f32.bf16.bf16 {%0,%1,%2,%3,%4,%5,%6,%7,%8,%9,%10,%11,%12,%13,%14,%15,%16,%17,%18,%19,%20,%21,%22,%23,%24,%25,%26,%27,%28,%29,%30,%31}, {%32,%33,%34,%35}, %36, 0, 1, 1, %37;"
   : "=f"(d[O+0]), "=f"(d[O+1]), "=f"(d[O+2]), "=f"(d[O+3]), "=f"(d[O+4]), "=f"(d[O+5]), "=f"(d[O+6]), "=f"(d[O+7]), "=f"(d[O+8]), "=f"(d[O+9]), "=f"(d[O+10]), "=f"(d[O+11]), "=f"(d[O+12]), "=f"(d[O+13]), "=f"(d[O+14]), "=f"(d[O+15]), "=f"(d[O+16]), "=f"(d[O+17]), "=f"(d[O+18]), "=f"(d[O+19]), "=f"(d[O+20]), "=f"(d[O+21]), "=f"(d[O+22]), "=f"(d[O+23]), "=f"(d[O+24]), "=f"(d[O+25]), "=f"(d[O+26]), "=f"(d[O+27]), "=f"(d[O+28]), "=f"(d[O+29]), "=f"(d[O+30]), "=f"(d[O+31])
   : "r"(a0), "r"(a1), "r"(a2), "r"(a3), "l"(db), "n"(TB));
  else asm volatile("{\n.reg .pred p;\nsetp.ne.b32 p, %38, 0;\nwgmma.mma_async.sync.aligned.m64n64k16.f32.bf16.bf16 {%0,%1,%2,%3,%4,%5,%6,%7,%8,%9,%10,%11,%12,%13,%14,%15,%16,%17,%18,%19,%20,%21,%22,%23,%24,%25,%26,%27,%28,%29,%30,%31}, {%32,%33,%34,%35}, %36, p, 1, 1, %37;\n}"
   : "+f"(d[O+0]), "+f"(d[O+1]), "+f"(d[O+2]), "+f"(d[O+3]), "+f"(d[O+4]), "+f"(d[O+5]), "+f"(d[O+6]), "+f"(d[O+7]), "+f"(d[O+8]), "+f"(d[O+9]), "+f"(d[O+10]), "+f"(d[O+11]), "+f"(d[O+12]), "+f"(d[O+13]), "+f"(d[O+14]), "+f"(d[O+15]), "+f"(d[O+16]), "+f"(d[O+17]), "+f"(d[O+18]), "+f"(d[O+19]), "+f"(d[O+20]), "+f"(d[O+21]), "+f"(d[O+22]), "+f"(d[O+23]), "+f"(d[O+24]), "+f"(d[O+25]), "+f"(d[O+26]), "+f"(d[O+27]), "+f"(d[O+28]), "+f"(d[O+29]), "+f"(d[O+30]), "+f"(d[O+31])
   : "r"(a0), "r"(a1), "r"(a2), "r"(a3), "l"(db), "n"(TB), "r"(sd));
}
template<int O,int TB,int ACC,int NN> __device__ __forceinline__ void mma_ss128(float (&d)[NN], uint64_t da, uint64_t db, int sd = 0){
  if constexpr (ACC == 1) asm volatile("wgmma.mma_async.sync.aligned.m64n128k16.f32.bf16.bf16 {%0,%1,%2,%3,%4,%5,%6,%7,%8,%9,%10,%11,%12,%13,%14,%15,%16,%17,%18,%19,%20,%21,%22,%23,%24,%25,%26,%27,%28,%29,%30,%31,%32,%33,%34,%35,%36,%37,%38,%39,%40,%41,%42,%43,%44,%45,%46,%47,%48,%49,%50,%51,%52,%53,%54,%55,%56,%57,%58,%59,%60,%61,%62,%63}, %64, %65, 1, 1, 1, %67, %66;"
   : "+f"(d[O+0]), "+f"(d[O+1]), "+f"(d[O+2]), "+f"(d[O+3]), "+f"(d[O+4]), "+f"(d[O+5]), "+f"(d[O+6]), "+f"(d[O+7]), "+f"(d[O+8]), "+f"(d[O+9]), "+f"(d[O+10]), "+f"(d[O+11]), "+f"(d[O+12]), "+f"(d[O+13]), "+f"(d[O+14]), "+f"(d[O+15]), "+f"(d[O+16]), "+f"(d[O+17]), "+f"(d[O+18]), "+f"(d[O+19]), "+f"(d[O+20]), "+f"(d[O+21]), "+f"(d[O+22]), "+f"(d[O+23]), "+f"(d[O+24]), "+f"(d[O+25]), "+f"(d[O+26]), "+f"(d[O+27]), "+f"(d[O+28]), "+f"(d[O+29]), "+f"(d[O+30]), "+f"(d[O+31]), "+f"(d[O+32]), "+f"(d[O+33]), "+f"(d[O+34]), "+f"(d[O+35]), "+f"(d[O+36]), "+f"(d[O+37]), "+f"(d[O+38]), "+f"(d[O+39]), "+f"(d[O+40]), "+f"(d[O+41]), "+f"(d[O+42]), "+f"(d[O+43]), "+f"(d[O+44]), "+f"(d[O+45]), "+f"(d[O+46]), "+f"(d[O+47]), "+f"(d[O+48]), "+f"(d[O+49]), "+f"(d[O+50]), "+f"(d[O+51]), "+f"(d[O+52]), "+f"(d[O+53]), "+f"(d[O+54]), "+f"(d[O+55]), "+f"(d[O+56]), "+f"(d[O+57]), "+f"(d[O+58]), "+f"(d[O+59]), "+f"(d[O+60]), "+f"(d[O+61]), "+f"(d[O+62]), "+f"(d[O+63])
   : "l"(da), "l"(db), "n"(TB & 1), "n"(TB >> 1));
  else if constexpr (ACC == 0) asm volatile("wgmma.mma_async.sync.aligned.m64n128k16.f32.bf16.bf16 {%0,%1,%2,%3,%4,%5,%6,%7,%8,%9,%10,%11,%12,%13,%14,%15,%16,%17,%18,%19,%20,%21,%22,%23,%24,%25,%26,%27,%28,%29,%30,%31,%32,%33,%34,%35,%36,%37,%38,%39,%40,%41,%42,%43,%44,%45,%46,%47,%48,%49,%50,%51,%52,%53,%54,%55,%56,%57,%58,%59,%60,%61,%62,%63}, %64, %65, 0, 1, 1, %67, %66;"
   : "=f"(d[O+0]), "=f"(d[O+1]), "=f"(d[O+2]), "=f"(d[O+3]), "=f"(d[O+4]), "=f"(d[O+5]), "=f"(d[O+6]), "=f"(d[O+7]), "=f"(d[O+8]), "=f"(d[O+9]), "=f"(d[O+10]), "=f"(d[O+11]), "=f"(d[O+12]), "=f"(d[O+13]), "=f"(d[O+14]), "=f"(d[O+15]), "=f"(d[O+16]), "=f"(d[O+17]), "=f"(d[O+18]), "=f"(d[O+19]), "=f"(d[O+20]), "=f"(d[O+21]), "=f"(d[O+22]), "=f"(d[O+23]), "=f"(d[O+24]), "=f"(d[O+25]), "=f"(d[O+26]), "=f"(d[O+27]), "=f"(d[O+28]), "=f"(d[O+29]), "=f"(d[O+30]), "=f"(d[O+31]), "=f"(d[O+32]), "=f"(d[O+33]), "=f"(d[O+34]), "=f"(d[O+35]), "=f"(d[O+36]), "=f"(d[O+37]), "=f"(d[O+38]), "=f"(d[O+39]), "=f"(d[O+40]), "=f"(d[O+41]), "=f"(d[O+42]), "=f"(d[O+43]), "=f"(d[O+44]), "=f"(d[O+45]), "=f"(d[O+46]), "=f"(d[O+47]), "=f"(d[O+48]), "=f"(d[O+49]), "=f"(d[O+50]), "=f"(d[O+51]), "=f"(d[O+52]), "=f"(d[O+53]), "=f"(d[O+54]), "=f"(d[O+55]), "=f"(d[O+56]), "=f"(d[O+57]), "=f"(d[O+58]), "=f"(d[O+59]), "=f"(d[O+60]), "=f"(d[O+61]), "=f"(d[O+62]), "=f"(d[O+63])
   : "l"(da), "l"(db), "n"(TB & 1), "n"(TB >> 1));
  else asm volatile("{\n.reg .pred p;\nsetp.ne.b32 p, %68, 0;\nwgmma.mma_async.sync.aligned.m64n128k16.f32.bf16.bf16 {%0,%1,%2,%3,%4,%5,%6,%7,%8,%9,%10,%11,%12,%13,%14,%15,%16,%17,%18,%19,%20,%21,%22,%23,%24,%25,%26,%27,%28,%29,%30,%31,%32,%33,%34,%35,%36,%37,%38,%39,%40,%41,%42,%43,%44,%45,%46,%47,%48,%49,%50,%51,%52,%53,%54,%55,%56,%57,%58,%59,%60,%61,%62,%63}, %64, %65, p, 1, 1, %67, %66;\n}"
   : "+f"(d[O+0]), "+f"(d[O+1]), "+f"(d[O+2]), "+f"(d[O+3]), "+f"(d[O+4]), "+f"(d[O+5]), "+f"(d[O+6]), "+f"(d[O+7]), "+f"(d[O+8]), "+f"(d[O+9]), "+f"(d[O+10]), "+f"(d[O+11]), "+f"(d[O+12]), "+f"(d[O+13]), "+f"(d[O+14]), "+f"(d[O+15]), "+f"(d[O+16]), "+f"(d[O+17]), "+f"(d[O+18]), "+f"(d[O+19]), "+f"(d[O+20]), "+f"(d[O+21]), "+f"(d[O+22]), "+f"(d[O+23]), "+f"(d[O+24]), "+f"(d[O+25]), "+f"(d[O+26]), "+f"(d[O+27]), "+f"(d[O+28]), "+f"(d[O+29]), "+f"(d[O+30]), "+f"(d[O+31]), "+f"(d[O+32]), "+f"(d[O+33]), "+f"(d[O+34]), "+f"(d[O+35]), "+f"(d[O+36]), "+f"(d[O+37]), "+f"(d[O+38]), "+f"(d[O+39]), "+f"(d[O+40]), "+f"(d[O+41]), "+f"(d[O+42]), "+f"(d[O+43]), "+f"(d[O+44]), "+f"(d[O+45]), "+f"(d[O+46]), "+f"(d[O+47]), "+f"(d[O+48]), "+f"(d[O+49]), "+f"(d[O+50]), "+f"(d[O+51]), "+f"(d[O+52]), "+f"(d[O+53]), "+f"(d[O+54]), "+f"(d[O+55]), "+f"(d[O+56]), "+f"(d[O+57]), "+f"(d[O+58]), "+f"(d[O+59]), "+f"(d[O+60]), "+f"(d[O+61]), "+f"(d[O+62]), "+f"(d[O+63])
   : "l"(da), "l"(db), "n"(TB & 1), "n"(TB >> 1), "r"(sd));
}
template<int O,int TB,int ACC,int NN> __device__ __forceinline__ void mma_rs128(float (&d)[NN], uint32_t a0, uint32_t a1, uint32_t a2, uint32_t a3, uint64_t db, int sd = 0){
  if constexpr (ACC == 1) asm volatile("wgmma.mma_async.sync.aligned.m64n128k16.f32.bf16.bf16 {%0,%1,%2,%3,%4,%5,%6,%7,%8,%9,%10,%11,%12,%13,%14,%15,%16,%17,%18,%19,%20,%21,%22,%23,%24,%25,%26,%27,%28,%29,%30,%31,%32,%33,%34,%35,%36,%37,%38,%39,%40,%41,%42,%43,%44,%45,%46,%47,%48,%49,%50,%51,%52,%53,%54,%55,%56,%57,%58,%59,%60,%61,%62,%63}, {%64,%65,%66,%67}, %68, 1, 1, 1, %69;"
   : "+f"(d[O+0]), "+f"(d[O+1]), "+f"(d[O+2]), "+f"(d[O+3]), "+f"(d[O+4]), "+f"(d[O+5]), "+f"(d[O+6]), "+f"(d[O+7]), "+f"(d[O+8]), "+f"(d[O+9]), "+f"(d[O+10]), "+f"(d[O+11]), "+f"(d[O+12]), "+f"(d[O+13]), "+f"(d[O+14]), "+f"(d[O+15]), "+f"(d[O+16]), "+f"(d[O+17]), "+f"(d[O+18]), "+f"(d[O+19]), "+f"(d[O+20]), "+f"(d[O+21]), "+f"(d[O+22]), "+f"(d[O+23]), "+f"(d[O+24]), "+f"(d[O+25]), "+f"(d[O+26]), "+f"(d[O+27]), "+f"(d[O+28]), "+f"(d[O+29]), "+f"(d[O+30]), "+f"(d[O+31]), "+f"(d[O+32]), "+f"(d[O+33]), "+f"(d[O+34]), "+f"(d[O+35]), "+f"(d[O+36]), "+f"(d[O+37]), "+f"(d[O+38]), "+f"(d[O+39]), "+f"(d[O+40]), "+f"(d[O+41]), "+f"(d[O+42]), "+f"(d[O+43]), "+f"(d[O+44]), "+f"(d[O+45]), "+f"(d[O+46]), "+f"(d[O+47]), "+f"(d[O+48]), "+f"(d[O+49]), "+f"(d[O+50]), "+f"(d[O+51]), "+f"(d[O+52]), "+f"(d[O+53]), "+f"(d[O+54]), "+f"(d[O+55]), "+f"(d[O+56]), "+f"(d[O+57]), "+f"(d[O+58]), "+f"(d[O+59]), "+f"(d[O+60]), "+f"(d[O+61]), "+f"(d[O+62]), "+f"(d[O+63])
   : "r"(a0), "r"(a1), "r"(a2), "r"(a3), "l"(db), "n"(TB));
  else if constexpr (ACC == 0) asm volatile("wgmma.mma_async.sync.aligned.m64n128k16.f32.bf16.bf16 {%0,%1,%2,%3,%4,%5,%6,%7,%8,%9,%10,%11,%12,%13,%14,%15,%16,%17,%18,%19,%20,%21,%22,%23,%24,%25,%26,%27,%28,%29,%30,%31,%32,%33,%34,%35,%36,%37,%38,%39,%40,%41,%42,%43,%44,%45,%46,%47,%48,%49,%50,%51,%52,%53,%54,%55,%56,%57,%58,%59,%60,%61,%62,%63}, {%64,%65,%66,%67}, %68, 0, 1, 1, %69;"
   : "=f"(d[O+0]), "=f"(d[O+1]), "=f"(d[O+2]), "=f"(d[O+3]), "=f"(d[O+4]), "=f"(d[O+5]), "=f"(d[O+6]), "=f"(d[O+7]), "=f"(d[O+8]), "=f"(d[O+9]), "=f"(d[O+10]), "=f"(d[O+11]), "=f"(d[O+12]), "=f"(d[O+13]), "=f"(d[O+14]), "=f"(d[O+15]), "=f"(d[O+16]), "=f"(d[O+17]), "=f"(d[O+18]), "=f"(d[O+19]), "=f"(d[O+20]), "=f"(d[O+21]), "=f"(d[O+22]), "=f"(d[O+23]), "=f"(d[O+24]), "=f"(d[O+25]), "=f"(d[O+26]), "=f"(d[O+27]), "=f"(d[O+28]), "=f"(d[O+29]), "=f"(d[O+30]), "=f"(d[O+31]), "=f"(d[O+32]), "=f"(d[O+33]), "=f"(d[O+34]), "=f"(d[O+35]), "=f"(d[O+36]), "=f"(d[O+37]), "=f"(d[O+38]), "=f"(d[O+39]), "=f"(d[O+40]), "=f"(d[O+41]), "=f"(d[O+42]), "=f"(d[O+43]), "=f"(d[O+44]), "=f"(d[O+45]), "=f"(d[O+46]), "=f"(d[O+47]), "=f"(d[O+48]), "=f"(d[O+49]), "=f"(d[O+50]), "=f"(d[O+51]), "=f"(d[O+52]), "=f"(d[O+53]), "=f"(d[O+54]), "=f"(d[O+55]), "=f"(d[O+56]), "=f"(d[O+57]), "=f"(d[O+58]), "=f"(d[O+59]), "=f"(d[O+60]), "=f"(d[O+61]), "=f"(d[O+62]), "=f"(d[O+63])
   : "r"(a0), "r"(a1), "r"(a2), "r"(a3), "l"(db), "n"(TB));
  else asm volatile("{\n.reg .pred p;\nsetp.ne.b32 p, %70, 0;\nwgmma.mma_async.sync.aligned.m64n128k16.f32.bf16.bf16 {%0,%1,%2,%3,%4,%5,%6,%7,%8,%9,%10,%11,%12,%13,%14,%15,%16,%17,%18,%19,%20,%21,%22,%23,%24,%25,%26,%27,%28,%29,%30,%31,%32,%33,%34,%35,%36,%37,%38,%39,%40,%41,%42,%43,%44,%45,%46,%47,%48,%49,%50,%51,%52,%53,%54,%55,%56,%57,%58,%59,%60,%61,%62,%63}, {%64,%65,%66,%67}, %68, p, 1, 1, %69;\n}"
   : "+f"(d[O+0]), "+f"(d[O+1]), "+f"(d[O+2]), "+f"(d[O+3]), "+f"(d[O+4]), "+f"(d[O+5]), "+f"(d[O+6]), "+f"(d[O+7]), "+f"(d[O+8]), "+f"(d[O+9]), "+f"(d[O+10]), "+f"(d[O+11]), "+f"(d[O+12]), "+f"(d[O+13]), "+f"(d[O+14]), "+f"(d[O+15]), "+f"(d[O+16]), "+f"(d[O+17]), "+f"(d[O+18]), "+f"(d[O+19]), "+f"(d[O+20]), "+f"(d[O+21]), "+f"(d[O+22]), "+f"(d[O+23]), "+f"(d[O+24]), "+f"(d[O+25]), "+f"(d[O+26]), "+f"(d[O+27]), "+f"(d[O+28]), "+f"(d[O+29]), "+f"(d[O+30]), "+f"(d[O+31]), "+f"(d[O+32]), "+f"(d[O+33]), "+f"(d[O+34]), "+f"(d[O+35]), "+f"(d[O+36]), "+f"(d[O+37]), "+f"(d[O+38]), "+f"(d[O+39]), "+f"(d[O+40]), "+f"(d[O+41]), "+f"(d[O+42]), "+f"(d[O+43]), "+f"(d[O+44]), "+f"(d[O+45]), "+f"(d[O+46]), "+f"(d[O+47]), "+f"(d[O+48]), "+f"(d[O+49]), "+f"(d[O+50]), "+f"(d[O+51]), "+f"(d[O+52]), "+f"(d[O+53]), "+f"(d[O+54]), "+f"(d[O+55]), "+f"(d[O+56]), "+f"(d[O+57]), "+f"(d[O+58]), "+f"(d[O+59]), "+f"(d[O+60]), "+f"(d[O+61]), "+f"(d[O+62]), "+f"(d[O+63])
   : "r"(a0), "r"(a1), "r"(a2), "r"(a3), "l"(db), "n"(TB), "r"(sd));
}

#define NEARLY 0
#define XAHEAD 3
#define HM 2
#define SPACE 100
#define WAFTER 7
#define WPACE 100
#define GATE_AT 4
#define TPACE 40
#define PFMODE 0
#define MAPMODE 0
template <int V> struct IC { static constexpr int value = V; };
struct Maps { CUtensorMap x, ft, g64, u64, e, wr, wi, xs, ts, t, g32, u32, d224; };

constexpr int NCTA = 130;
constexpr int U = 16384;
constexpr int TB = 36864;
constexpr int NR = 4;
constexpr int OFF_RING = 8 * U, OFF_Z = 9 * U, OFF_XB = 12 * U, OFF_T = 13 * U, OFF_D = OFF_T;
constexpr int OFF_BAR = 14 * U, OFF_SP = OFF_BAR + 512;
constexpr int SMEM_BYTES = OFF_SP + 1024;
constexpr int B_FX = 0, B_FA = 8, B_FT = 12, B_Z = 16, B_W = 20, B_HX = 21, B_TL = 22, B_HP = 23, B_WR = 26;
constexpr int B_EA = 30, B_ET = 34, B_RDY = 38, B_C1 = 39, B_PZ = 40;
constexpr int B_T = 42, B_XS = 43, NBAR = 45;
__host__ __device__ constexpr int rslot(int n) { return n & 3; }
__host__ __device__ constexpr int rpar(int n) { return (n >> 2) & 1; }

__global__ void __cluster_dims__(2, 1, 1) __launch_bounds__(512, 1)
fused_kernel(const __grid_constant__ Maps maps, const __nv_bfloat16* __restrict__ x, const __nv_bfloat16* __restrict__ w_r,
             const __nv_bfloat16* __restrict__ w_i, const __nv_bfloat16* __restrict__ gate_w, __nv_bfloat16* __restrict__ out) {
  extern __shared__ __align__(1024) uint8_t smem[];
  const uint32_t sb = smem_u32(smem);
  const uint32_t bars = sb + OFF_BAR;
  const int tid = threadIdx.x, lane = tid & 31;
  const int warp = __shfl_sync(0xffffffffu, tid >> 5, 0);
  const bool helper = blockIdx.x >= 128;
  const int cl = (blockIdx.x >> 1) & 63, rank = blockIdx.x & 1;
  const int q4 = cl & 3, rb = cl >> 2;
  const int j = 2 * q4 + rank;
  const int f_full = 448 * q4 + (rank ? 256 : 0);
  const int f_half = 448 * q4 + (rank ? 224 : 192);
  const int kg = 2 * j + (rb >> 3), tn = rb & 7;

  if (tid == 64) { PROF_EV(0); PROF_CK(40); }
  auto ring_part = [&](int p, int n, int slot) {
    const uint32_t fb = bars + 8 * (B_FA + slot), dst = sb + OFF_RING + slot * U + p * 8192;
    const bool table = n == 8 || n == 9 || n >= 30;
    const int q = n < 8 ? n : n - 2;
    if (p == 0) {
      mbar_expect_tx(fb, n < 8 ? U + 8192 : U);
    }
    if (table) { if (p == 0) tma4d(dst, &maps.e, fb, 0, 0, 0, 2 * rb + (n & 1)); }
    else if (n >= 26) tma2d(dst, p ? &maps.u32 : &maps.g32, fb, f_half, 128 * (n - 26));
    else {
      if (n < 8 && p == 1) tma2d(sb + OFF_XB + slot * 8192, &maps.ft, fb, 64 * n, 64 * j);
      tma2d(dst, p ? &maps.u64 : &maps.g64, fb, f_full + 64 * (q >> 3), 64 * (q & 7));
    }
  };
  auto x_load = [&](int q) {
    mbar_expect_tx(bars + 8 * (B_FX + q), U);
    tma3d(sb + q * U, &maps.x, bars + 8 * (B_FX + q), 64 * q, 0, 2 * rb);
  };
  if (warp < 8) {
    asm volatile("barrier.cluster.arrive.relaxed.aligned;" ::: "memory");
    asm volatile("setmaxnreg.inc.sync.aligned.u32 192;");
    if (tid == 0) PROF_EV(33);
    if (!helper) {
      const int wg = warp >> 2, w = warp & 3, g = lane >> 2, q = lane & 3;
      const bool elect = (tid & 127) == 0;
      float cX[32], cA[64], cB[64], ci[64], ct[64];
      const int zero = blockIdx.x >> 16;
      uint32_t h[56], yf[16];
      const uint32_t d0 = (sb & 0x3FFFF) >> 4;
      const uint32_t dK = d0 | (1u << 16), dN = d0 | (512u << 16);
      const uint32_t dX = dK + wg * 512;
      constexpr uint32_t RING = OFF_RING >> 4;
      auto waitA = [&](int n) { mbar_wait(bars + 8 * (B_FA + rslot(n)), rpar(n)); };
      auto freeA = [&](int n) { if (elect) mbar_arrive(bars + 8 * (B_EA + rslot(n))); };
      auto nop = [](int) {};

      if (tid == 0) PROF_EV(34);
      asm volatile("bar.sync 0, 384;" ::: "memory");
      if (tid == 0) PROF_EV(35);
#pragma unroll 1
      for (int kb = 0; kb < 8; kb++) {
        mbar_wait(bars + 8 * (B_FX + kb), 0);
        if (tid == 0 && kb == 0) PROF_EV(36);
        waitA(kb);
        wg_fence();
        const uint64_t dx = d128(dX + kb * 1024), df = d128(dK + (OFF_XB >> 4) + rslot(kb) * 512), db = d128(dN + RING + rslot(kb) * 1024);
        mma_ss64<0, 0, 2>(cX, df, dx, kb);
        mma_ss64<0, 0, 1>(cX, df + 2, dx + 2);
        wg_commit(); wg_wait<1>();
        if (kb) freeA(kb - 1);
        mma_ss64<0, 0, 1>(cX, df + 4, dx + 4);
        mma_ss64<0, 0, 1>(cX, df + 6, dx + 6);
        wg_commit();
        mma_ss128<0, 1, 2>(cA, dx, db, kb);
#pragma unroll
        for (int k = 1; k < 4; k++) mma_ss128<0, 1, 1>(cA, dx + k * 2, db + k * 128);
        wg_commit();
        if (kb == 0 && tid == 0) PROF_EV(1);
      }
      wg_wait<1>();
      fence_regs<0, 32>(cX);
#pragma unroll
      for (int e = 0; e < 16; e++) yf[e] = pack_pin(cX[2 * e], cX[2 * e + 1]);
      if (tid == 0) PROF_EV(2);
      float o0 = 1.0f, o1 = 1.0f;
      auto glu = [&](auto scaled, auto& acc, int half, int ho, int i0, int i1) {
#pragma unroll
        for (int i = i0; i < i1; i++) {
          float a = fmaxf(acc[2 * i], 0.f) * acc[half + 2 * i], b = fmaxf(acc[2 * i + 1], 0.f) * acc[half + 1 + 2 * i];
          if (decltype(scaled)::value) { const float o = (i & 1) ? o1 : o0; a *= o; b *= o; }
          h[ho + i] = pack_pin(a, b);
        }
      };
      {
        waitA(8); waitA(9);
        const uint64_t de = d128(dN + RING + wg * 1024);
        wg_fence();
        mma_rs128<0, 1, 0>(cB, yf[0], yf[1], yf[2], yf[3], de);
        wg_commit();
        wg_wait<1>();
        freeA(7);
        if (elect) mbar_arrive(bars + 8 * B_C1);
        fence_regs<0, 64>(cA);
#pragma unroll
        for (int k = 1; k < 4; k++) { glu(IC<0>(), cA, 32, 0, 4 * k - 4, 4 * k); mma_rs128<0, 1, 1>(cB, yf[4 * k], yf[4 * k + 1], yf[4 * k + 2], yf[4 * k + 3], de + k * 128); }
        wg_commit();
        glu(IC<0>(), cA, 32, 0, 12, 16);
      }
      auto ffn_step = [&](auto first, float (&acc)[64], int n, int kb, auto done, auto work) {
        waitA(n);
        wg_fence();
        const uint64_t dx = d128(dX + kb * 1024), db = d128(dN + RING + rslot(n) * 1024);
        mma_ss128<0, 1, decltype(first)::value>(acc, dx, db, zero);
        wg_commit();
        wg_wait<1>();
        done();
#pragma unroll
        for (int k = 1; k < 4; k++) { work(k - 1); mma_ss128<0, 1, 1>(acc, dx + k * 2, db + k * 128); }
        wg_commit();
        work(3);
      };
      {
        const int s0 = 2 * rb + wg, kr = 2 * ((s0 & 1) | ((s0 & 4) >> 1));
        const int m = lane >> 3, r = lane & 7;
        const uint32_t a0 = sb + OFF_XB + wg * 8192 + (((w >> 1) * 8 + (m >> 1)) * 2 + (w & 1)) * 256 + (m & 1) * 128 + ((r ^ (kr + (m & 1))) << 4);
        ffn_step(IC<2>(), cA, 10, 0, [&] { freeA(8); freeA(9); fence_regs<0, 64>(cB); }, [&](int i) {
          stsm4t(a0 + i * 1024, pack_bf16(cB[8 * i] - cB[34 + 8 * i], cB[8 * i + 1] - cB[35 + 8 * i]),
                 pack_bf16(cB[32 + 8 * i] + cB[8 * i + 2], cB[33 + 8 * i] + cB[8 * i + 3]),
                 pack_bf16(cB[8 * i + 4] - cB[38 + 8 * i], cB[8 * i + 5] - cB[39 + 8 * i]),
                 pack_bf16(cB[36 + 8 * i] + cB[8 * i + 6], cB[37 + 8 * i] + cB[8 * i + 7]));
        });
        if (j == 0 && w == 0 && g == 0) {
#pragma unroll
          for (int n = 0; n < 8; n++)
#pragma unroll
            for (int ce = 0; ce < 4; ce++)
              *(uint32_t*)(smem + OFF_SP + wg * 512 + ce * 128 + ((n ^ (kr + (ce & 1))) << 4) + 4 * q) =
                  pack_bf16(cB[(ce & 1) * 32 + 4 * n + (ce & 2)], cB[(ce & 1) * 32 + 4 * n + (ce & 2) + 1]);
        }
        ffn_step(IC<1>(), cA, 11, 1, [&] { freeA(10); }, [&](int i) {
          if (i == 1) {
            asm volatile("fence.proxy.async.shared::cta;" ::: "memory");
            __syncwarp();
            if (lane == 0) mbar_arrive(bars + 8 * (B_XS + wg));
            if (tid == 0) PROF_EV(3);
          }
        });
      }
      const float* gp = g_gate + rb * 128 + wg * 64 + w * 16 + g;
      uint32_t gb0 = 0, gb1 = 0, ep = 0;
#pragma unroll 1
      for (int kb = 2; kb < 8; kb++)
        ffn_step(IC<1>(), cA, 10 + kb, kb, [&] {
          freeA(9 + kb);
          if (kb == 4) { gb0 = ld_x1(gp); gb1 = ld_x1(gp + 8); ep = ld_x1(&g_epoch[blockIdx.x * 8 + (tid >> 12)]); }
        }, nop);
      asm volatile("" : "+r"(ep), "+r"(gb0), "+r"(gb1)::"memory");
      const uint32_t tag = (ep + 1) & 1;
      {
        const uint32_t t0 = (uint32_t)clock();
        while (__any_sync(0xffffffffu, ((gb0 ^ tag) | (gb1 ^ tag)) & 1)) { gb0 = ld_x1(gp); gb1 = ld_x1(gp + 8); spin_guard(t0); }
      }
      const float g0 = __uint_as_float(gb0 & ~1u), g1 = __uint_as_float(gb1 & ~1u);
      o0 = 1.0f - g0; o1 = 1.0f - g1;
      ffn_step(IC<2>(), cB, 18, 0, [&] { freeA(17); fence_regs<0, 64>(cA); }, [&](int i) { glu(IC<1>(), cA, 32, 16, 2 * i, 2 * i + 2); });
      if (tid == 0) PROF_EV(4);
      ffn_step(IC<1>(), cB, 19, 1, [&] { freeA(18); }, [&](int i) { glu(IC<1>(), cA, 32, 16, 8 + 2 * i, 10 + 2 * i); });
      ffn_step(IC<1>(), cB, 20, 2, [&] { freeA(19); }, [&](int i) {
#pragma unroll
        for (int e = 4 * i; e < 4 * i + 4; e++) { const float o = (e & 1) ? o1 : o0; h[e] = pack_pin(bf_lo(h[e]) * o, bf_hi(h[e]) * o); }
      });
#pragma unroll 1
      for (int kb = 3; kb < 8; kb++) ffn_step(IC<1>(), cB, 18 + kb, kb, [&] { freeA(17 + kb); }, nop);
      if (tid == 0) PROF_EV(5);
      auto m_step = [&](auto first, int i, auto done, auto work) {
        waitA(26 + i);
        wg_fence();
        const uint64_t dx = d128(dX + i * 2048), dm = d64(dN + RING + rslot(26 + i) * 1024);
        mma_ss64<0, 1, decltype(first)::value>(ct, dx, dm);
        mma_ss64<0, 1, 1>(ct, dx + 2, dm + 64);
        wg_commit();
        wg_wait<1>();
        done();
#pragma unroll
        for (int k = 2; k < 8; k++) { if (k & 1) work(k / 2 - 1); mma_ss64<0, 1, 1>(ct, dx + ((k >> 2) * 1024 + (k & 3) * 2), dm + k * 64); }
        wg_commit();
        work(3);
      };
      auto freeT = [&](int t) { if (elect) mbar_arrive(bars + 8 * (B_ET + t)); };
      m_step(IC<0>(), 0, [&] { freeA(25); fence_regs<0, 64>(cB); }, [&](int i) { glu(IC<1>(), cB, 32, 32, 2 * i, 2 * i + 2); });
      m_step(IC<1>(), 1, [&] { freeA(26); freeT(0); }, [&](int i) { glu(IC<1>(), cB, 32, 32, 8 + 2 * i, 10 + 2 * i); });
#pragma unroll 1
      for (int i = 2; i < 4; i++) m_step(IC<1>(), i, [&] { freeA(25 + i); freeT(i - 1); }, nop);
      if (wg) waitA(31); else waitA(30);
      if (tid == 0) PROF_EV(6);
      mbar_wait(bars + 8 * (j == 0 ? B_T : B_TL), 0);
      if (tid == 0) PROF_EV(7);
      wg_fence();
      {
        const uint64_t dt = d128(dN + (OFF_T >> 4) + wg * 512), de = d128(dK + RING + (2 + wg) * 1024);
        mma_ss64<0, 1, 0>(ci, de, dt);
        mma_ss64<32, 1, 0>(ci, de + 512, dt);
        wg_commit();
        wg_wait<1>();
        freeT(3);
        fence_regs<0, 32>(ct);
#pragma unroll
        for (int k = 1; k < 4; k++) {
          mma_ss64<0, 1, 1>(ci, de + k * 2, dt + k * 128);
          mma_ss64<32, 1, 1>(ci, de + (512 + k * 2), dt + k * 128);
          if (k < 3) glu(IC<1>(), ct, 16, 48, 4 * k - 4, 4 * k);
        }
        wg_commit();
      }

      auto head = [&](auto off, int t, auto first) {
        constexpr int O = decltype(off)::value;
        mbar_wait(bars + 8 * (B_FT + (t & 3)), t >> 2);
        const uint64_t db = d128(dN + (t & 3) * (TB >> 4) + rank * 256);
        wg_fence();
        mma_rs64<O, 1, decltype(first)::value>(ct, h[0], h[1], h[2], h[3], db, zero);
#pragma unroll
        for (int k = 1; k < 6; k++) mma_rs64<O, 1, 1>(ct, h[4 * k], h[4 * k + 1], h[4 * k + 2], h[4 * k + 3], db + k * 128);
        wg_commit();
        wg_wait<1>();
      };
      auto rest = [&](auto off, int t) {
        constexpr int O = decltype(off)::value;
        const uint64_t db = d128(dN + (t & 3) * (TB >> 4)), dw = db + rank * 256, dm = db + (rank ? 0 : 1536);
        wg_fence();
#pragma unroll
        for (int k = 6; k < 12; k++) mma_rs64<O, 1, 1>(ct, h[4 * k], h[4 * k + 1], h[4 * k + 2], h[4 * k + 3], dw + k * 128);
#pragma unroll
        for (int k = 0; k < 2; k++) mma_rs64<O, 1, 1>(ct, h[48 + 4 * k], h[49 + 4 * k], h[50 + 4 * k], h[51 + 4 * k], dm + k * 128);
#pragma unroll
        for (int k = 0; k < 4; k++) mma_rs64<O, 1, 1>(ct, yf[4 * k], yf[4 * k + 1], yf[4 * k + 2], yf[4 * k + 3], db + (14 + k) * 128);
        wg_commit();
      };
      const uint32_t peerZ = mapa(sb + OFF_Z + tid * 16, rank ^ 1), peerB = mapa(bars + 8 * B_Z, rank ^ 1);
      auto send = [&](auto off, int t) {
        constexpr int O = decltype(off)::value;
        fence_regs<O, 32>(ct);
        const bool grid = t >= 3 && t < 6;
        const int z = grid ? t - 3 : t == 6 ? 3 : t;
        if (grid) {
          mbar_wait(bars + 8 * (B_Z + z), 0);
#pragma unroll
          for (int i = 0; i < 4; i++) {
            const uint4 p = *(const uint4*)(smem + OFF_Z + z * U + i * 4096 + tid * 16);
            const uint32_t a[4] = {p.x, p.y, p.z, p.w};
#pragma unroll
            for (int e = 0; e < 4; e++) { ct[O + 8 * i + 2 * e] += bf_lo(a[e]); ct[O + 8 * i + 2 * e + 1] += bf_hi(a[e]); }
          }
        }
        uint32_t pk[16];
#pragma unroll
        for (int i = 0; i < 16; i++) pk[i] = pack_bf16(ct[O + 2 * i], ct[O + 2 * i + 1]);
        if (grid) {
          const int owner = rb * 8 + 2 * ((q4 + z + 1) & 3) + rank;
          uint4* dst = g_part + (size_t)(owner * 3 + z) * 1024 + tid;
#pragma unroll
          for (int i = 0; i < 4; i++) st_x4(dst + i * 256, (pk[4 * i] & ~1u) | tag, pk[4 * i + 1], pk[4 * i + 2], pk[4 * i + 3]);
          __syncwarp();
          if (lane == 0) hint_add(&g_cntP[32 * owner + z]);
        } else {
#pragma unroll
          for (int i = 0; i < 4; i++)
            asm volatile("st.async.weak.shared::cluster.mbarrier::complete_tx::bytes.v4.b32 [%0], {%1,%2,%3,%4}, [%5];" ::"r"(peerZ + z * U + i * 4096),
                         "r"(pk[4 * i]), "r"(pk[4 * i + 1]), "r"(pk[4 * i + 2]), "r"(pk[4 * i + 3]), "r"(peerB + 8 * z) : "memory");
        }
      };
      asm volatile("barrier.cluster.wait.aligned;" ::: "memory");
      head(IC<0>(), 0, IC<2>());
      if (elect) asm volatile("mbarrier.arrive.shared::cluster.b64 _, [%0];" ::"r"(mapa(bars + 8 * B_RDY, rank ^ 1)) : "memory");
      fence_regs<0, 64>(ci);
#pragma unroll
      for (int i = 0; i < 16; i++) {
        const float gg = ((i & 1) ? g1 : g0) * (2.0f / (2048.0f * 512.0f));
        if (i & 2) yf[i] = pack_pin((ci[2 * i] - ci[28 + 2 * i]) * gg, (ci[2 * i + 1] - ci[29 + 2 * i]) * gg);
        else yf[i] = pack_pin((ci[2 * i] + ci[36 + 2 * i]) * gg, (ci[2 * i + 1] + ci[37 + 2 * i]) * gg);
      }
      if (tid == 0) PROF_EV(8);
#pragma unroll 1
      for (int t = 0;; t += 2) {
        rest(IC<0>(), t);
        head(IC<32>(), t + 1, IC<2>());
        if (t < 4) freeT(t); else if (t == 4 && elect) mbar_arrive(bars + 8 * B_PZ);
        if (t == 0) mbar_wait(bars + 8 * B_RDY, 0);
        send(IC<0>(), t);
        rest(IC<32>(), t + 1);
        if (t == 6) break;
        head(IC<0>(), t + 2, IC<2>());
        if (t < 4) freeT(t + 1); else if (elect) mbar_arrive(bars + 8 * (B_PZ + 1));
        send(IC<32>(), t + 1);
      }
      if (tid == 0) PROF_EV(9);
      {
        float sum[32];
        mbar_wait(bars + 8 * (B_Z + 3), 0);
#pragma unroll
        for (int i = 0; i < 4; i++) {
          const uint4 p = *(const uint4*)(smem + OFF_Z + 3 * U + i * 4096 + tid * 16);
          const uint32_t a[4] = {p.x, p.y, p.z, p.w};
#pragma unroll
          for (int e = 0; e < 4; e++) { sum[8 * i + 2 * e] = bf_lo(a[e]); sum[8 * i + 2 * e + 1] = bf_hi(a[e]); }
        }
#pragma unroll 1
        for (int z = 0; z < 3; z++) {
          mbar_wait(bars + 8 * (B_HP + z), 0);
          if (z == 2 && tid == 0) PROF_EV(24);
          uint4 pv[4];
#pragma unroll
          for (int i = 0; i < 4; i++) pv[i] = *(const uint4*)(smem + z * U + i * 4096 + tid * 16);
          const uint32_t t0 = (uint32_t)clock();
          while (__any_sync(0xffffffffu, ((pv[0].x ^ tag) | (pv[1].x ^ tag) | (pv[2].x ^ tag) | (pv[3].x ^ tag)) & 1)) {
#pragma unroll
            for (int i = 0; i < 4; i++) pv[i] = ld_x4(g_part + (size_t)((rb * 8 + j) * 3 + z) * 1024 + tid + i * 256);
            spin_guard(t0);
          }
#pragma unroll
          for (int i = 0; i < 4; i++) {
            const uint32_t a[4] = {pv[i].x & ~1u, pv[i].y, pv[i].z, pv[i].w};
#pragma unroll
            for (int e = 0; e < 4; e++) { sum[8 * i + 2 * e] += bf_lo(a[e]); sum[8 * i + 2 * e + 1] += bf_hi(a[e]); }
          }
        }
        if (tid == 0) PROF_EV(14);
        wg_wait<0>();
        fence_regs<32, 32>(ct);
#pragma unroll
        for (int i = 0; i < 32; i++) sum[i] += ct[32 + i];
        const uint32_t stg = sb + OFF_T + warp * 2048;
        const int mr = (lane & 7) + ((lane >> 3) & 1) * 8, mc = lane >> 4;
#pragma unroll
        for (int i = 0; i < 4; i++) {
          const uint32_t a = stg + mr * 128 + (((2 * i + mc) ^ (mr & 7)) << 4);
          asm volatile("stmatrix.sync.aligned.m8n8.x4.shared.b16 [%0], {%1,%2,%3,%4};" ::"r"(a), "r"(pack_bf16(sum[8 * i], sum[8 * i + 1])),
                       "r"(pack_bf16(sum[8 * i + 2], sum[8 * i + 3])), "r"(pack_bf16(sum[8 * i + 4], sum[8 * i + 5])),
                       "r"(pack_bf16(sum[8 * i + 6], sum[8 * i + 7])) : "memory");
        }
        __syncwarp();
#pragma unroll
        for (int i = 0; i < 4; i++) {
          const int r = 4 * i + (lane >> 3), c = lane & 7;
          const uint4 v = *(const uint4*)(smem + OFF_T + warp * 2048 + r * 128 + ((c ^ (r & 7)) << 4));
          *(uint4*)(out + (size_t)(2 * rb + wg + 32 * (16 * w + r)) * 512 + 64 * j + 8 * c) = v;
        }
      }
      if (tid == 0) { g_epoch[blockIdx.x * 8] = ep + 1; PROF_EV(15); PROF_CK(41); }
    }
  } else if (warp < 12) {
    asm volatile("setmaxnreg.dec.sync.aligned.u32 104;");
    asm volatile("barrier.cluster.arrive.relaxed.aligned;" ::: "memory");
    const int t = tid - 256, w = warp - 8;
    const uint32_t ep = ld_x1(&g_epoch[blockIdx.x * 8]);
    const uint32_t tag = (ep + 1) & 1;
    auto gate_rows = [&] {
      const int r = 16 * j + 4 * w + (lane >> 3);
      const uint4* px = (const uint4*)(x + (size_t)(2 * rb + (r >> 6) + 32 * (r & 63)) * 512) + (lane & 7);
      const uint4* pg = (const uint4*)gate_w + (lane & 7);
      {
        float a = 0.f;
#pragma unroll 1
        for (int i = 0; i < 8; i += 4) {
          uint4 u[4], v[4];
#pragma unroll
          for (int e = 0; e < 4; e++) { u[e] = __ldg(px + (i + e) * 8); v[e] = __ldg(pg + (i + e) * 8); }
#pragma unroll
          for (int e = 0; e < 4; e++) {
            a = fmaf(bf_lo(u[e].x), bf_lo(v[e].x), a); a = fmaf(bf_hi(u[e].x), bf_hi(v[e].x), a);
            a = fmaf(bf_lo(u[e].y), bf_lo(v[e].y), a); a = fmaf(bf_hi(u[e].y), bf_hi(v[e].y), a);
            a = fmaf(bf_lo(u[e].z), bf_lo(v[e].z), a); a = fmaf(bf_hi(u[e].z), bf_hi(v[e].z), a);
            a = fmaf(bf_lo(u[e].w), bf_lo(v[e].w), a); a = fmaf(bf_hi(u[e].w), bf_hi(v[e].w), a);
          }
        }
#pragma unroll
        for (int o = 4; o; o >>= 1) a += __shfl_xor_sync(0xffffffffu, a, o);
        if ((lane & 7) == 0)
          asm volatile("st.relaxed.gpu.global.f32 [%0], %1;" ::"l"(g_gate + rb * 128 + r), "f"(tagf(__fdividef(1.0f, 1.0f + __expf(-a)), tag)) : "memory");
        if (t == 0) PROF_EV(18);
      }
      if (w == 0) {
        const int c = lane >> 4, jj = 16 * blockIdx.x + (lane & 15), jm = (2048 - jj) & 2047;
        const unsigned short* pr = (const unsigned short*)w_r + 256 * c;
        const unsigned short* pi = (const unsigned short*)w_i + 256 * c;
        const float wr = 0.25f * (bf_lo(__ldg(pr + jj * 257)) + bf_lo(__ldg(pr + jm * 257)));
        const float wi = 0.25f * (bf_lo(__ldg(pi + jj * 257)) - bf_lo(__ldg(pi + jm * 257)));
        st_u2(g_Wh + c * 2048 + jj, c ? pack_bf16(-wi, wr) : pack_bf16(wr, wi), tag);
        __syncwarp();
        if (lane == 0) hint_add(&g_cntW[0]);
      }
    };
    {
      const int g = lane >> 2, q = lane & 3;
      uint32_t wf[32];
      if (!helper) {
        asm volatile("bar.sync 4, 256;" ::: "memory");
        mbar_wait(bars + 8 * (B_FX + GATE_AT), 0);
        gate_rows();
        const uint32_t wa = sb + OFF_T + w * (3072 + 4) + q * 48 + g * 2;
        mbar_wait(bars + 8 * B_C1, 0);
        if (t == 0) PROF_EV(32);
        __nanosleep(WPACE * w);
#pragma unroll 1
        for (int ri = 0; ri < 2; ri++) {
          if (lane == 0) {
            mbar_expect_tx(bars + 8 * (B_WR + w), 3072);
            tma4d(sb + OFF_T + w * 3072, ri ? &maps.wi : &maps.wr, bars + 8 * (B_WR + w), 16 * kg, 0, 2 * w, tn);
          }
          mbar_wait(bars + 8 * (B_WR + w), ri);
#pragma unroll
          for (int n2 = 0; n2 < 4; n2++) {
            uint32_t v[8];
#pragma unroll
            for (int i = 0; i < 8; i++)
              asm volatile("ld.shared.u16 %0, [%1];" : "=r"(v[i]) : "r"(wa + (2 * n2 + ((i >> 1) & 1)) * 192 + (i & 1) * (1536 + 2) + (i >> 2) * 16) : "memory");
#pragma unroll
            for (int i = 0; i < 8; i++) {
              uint32_t& d = wf[(i >> 2) * 16 + 4 * n2 + (i & 3)];
              d = __byte_perm(d, v[i], 0x5432);
              asm volatile("" : "+r"(d)::"memory");
            }
          }
          __syncwarp();
        }
        asm volatile("bar.sync 1, 128;" ::: "memory");
        if (t == 0) PROF_EV(11);
      } else {
        asm volatile("bar.sync 4, 256;" ::: "memory");
        hint_wait(&g_cntW[0], (ep + 1) * 128u);
        const uint32_t t0 = (uint32_t)clock();
#pragma unroll 1
        for (;;) {
          uint32_t bad = 0;
#pragma unroll
          for (int i = 0; i < 32; i++) {
            const float2 v = ld_x2((const float2*)g_Wh + (i >> 4) * 2048 + 16 * w + g + 8 * (i & 1) + 64 * q + ((i >> 1) & 7) * 256);
            wf[i] = __float_as_uint(v.x); bad |= __float_as_uint(v.y) ^ tag;
          }
          if (!__any_sync(0xffffffffu, bad & 1)) break;
          spin_guard(t0);
        }
        if (t == 0) PROF_EV(11);
      }
      if (t == 0) { mbar_expect_tx(bars + 8 * B_W, 8192); bulk_load(sb + OFF_D, g_DT.v, 8192, bars + 8 * B_W); }
      mbar_wait(bars + 8 * B_W, 0);
      mbar_wait(bars + 8 * B_HX, 0);
      if (t == 0) PROF_EV(12);
      const uint32_t dd = (sb & 0x3FFFF) >> 4;
      const uint64_t dF = d128((dd + (OFF_D >> 4)) | (512u << 16)), dI = d128((dd + (OFF_D >> 4)) | (1u << 16)), dA = d128((dd + (OFF_XB >> 4)) | (512u << 16));
      float az[32];
      const int zero = blockIdx.x >> 16;
      uint32_t pf[32];
#pragma unroll
      for (int mt = 0; mt < 2; mt++) {
        wg_fence();
        if (mt == 0) mma_ss64<0, 3, 0>(az, dA, dF);
        else mma_ss64<0, 3, 2>(az, dA + 512, dF, zero);
#pragma unroll
        for (int k = 1; k < 4; k++) mma_ss64<0, 3, 1>(az, dA + (mt * 512 + k * 128), dF + k * 128);
        wg_commit();
        wg_wait<0>();
        fence_regs<0, 32>(az);
#pragma unroll
        for (int i = 0; i < 16; i++) {
          const float wr = bf_lo(wf[16 * mt + i]), wi = bf_hi(wf[16 * mt + i]);
          pf[16 * mt + i] = pack_pin(fmaf(az[2 * i], wr, -az[2 * i + 1] * wi), fmaf(az[2 * i], wi, az[2 * i + 1] * wr));
        }
      }
      if (t == 0) PROF_EV(16);
#pragma unroll
      for (int mt = 0; mt < 2; mt++) {
        wg_fence();
        mma_rs64<0, 0, 2>(az, pf[16 * mt], pf[16 * mt + 1], pf[16 * mt + 2], pf[16 * mt + 3], dI, mt ? (int)helper : zero);
#pragma unroll
        for (int k = 1; k < 4; k++) mma_rs64<0, 0, 1>(az, pf[16 * mt + 4 * k], pf[16 * mt + 4 * k + 1], pf[16 * mt + 4 * k + 2], pf[16 * mt + 4 * k + 3], dI + k * 2);
        wg_commit();
        wg_wait<0>();
        fence_regs<0, 32>(az);
        if (!helper) {
          const int m = lane >> 3, r = lane & 7;
          const int sl = 2 * (m >> 1) + ((r >> 1) & 1) + 4 * (r >> 2);
          const uint32_t a0 = sb + OFF_XB + (2 * w + (m & 1)) * 2048 + sl * 64 + (((mt * 2 + (r & 1)) ^ (sl >> 1)) << 4);
#pragma unroll
          for (int i = 0; i < 4; i++)
            stsm4t(a0 + i * 512, pack_bf16(az[8 * i], az[8 * i + 1]), pack_bf16(az[8 * i + 2], az[8 * i + 3]), pack_bf16(az[8 * i + 4], az[8 * i + 5]),
                   pack_bf16(az[8 * i + 6], az[8 * i + 7]));
        }
      }
      if (helper) {
#pragma unroll
        for (int i = 0; i < 16; i++) {
          const int n = i >> 1, s0 = 8 * (n >> 1) + 2 * (n & 1) + (q & 1) + 4 * (q >> 1);
          if ((n & 1) == (int)(blockIdx.x & 1)) st_u2(g_Ts + s0 * 64 + 16 * w + g + 8 * (i & 1), pack_bf16(az[2 * i], az[2 * i + 1]), tag);
        }
        __syncwarp();
        if (lane == 0) hint_add(&g_cntH[0]);
        if (t == 0) { g_epoch[blockIdx.x * 8] = ep + 1; PROF_EV(13); }
      } else {
        asm volatile("fence.proxy.async.shared::cta;" ::: "memory");
        __syncwarp();
        if (lane == 0) {
          if (t == 0) PROF_EV(17);
          if (SPACE) __nanosleep(SPACE * w);
          asm volatile("cp.async.bulk.tensor.3d.global.shared::cta.bulk_group [%0, {%2, %3, %4}], [%1];" ::"l"(&maps.ts), "r"(sb + OFF_XB + w * 4096),
                       "r"(32 * kg), "r"(0), "r"(8 * tn + 2 * w) : "memory");
          bulk_done_signal(&g_cntT[32 * j]);
          if (t == 96) PROF_EV(13);
        }
        __syncwarp();
        if (j == 0) {
          hint_wait(&g_cntH[0], (ep + 1) * 8u);
          const uint32_t t0 = (uint32_t)clock();
          float2 v;
          do { v = ld_x2((const float2*)g_Ts + 2 * rb * 64 + t); spin_guard(t0); } while (__any_sync(0xffffffffu, (__float_as_uint(v.y) ^ tag) & 1));
          mbar_wait(bars + 8 * B_TL, 0);
          const uint32_t u = __float_as_uint(v.x);
          *(uint16_t*)(smem + OFF_T + t * 128 + ((t & 7) << 4)) = (uint16_t)u;
          *(uint16_t*)(smem + OFF_T + t * 128 + (((t & 7) ^ 1) << 4)) = (uint16_t)(u >> 16);
          asm volatile("fence.proxy.async.shared::cta;" ::: "memory");
          __syncwarp();
          if (lane == 0) mbar_arrive(bars + 8 * B_T);
        }
      }
    }
  } else {
    asm volatile("setmaxnreg.dec.sync.aligned.u32 24;");
    if (warp < 14) {
      if (lane == 0) {
#pragma unroll
        for (int i = 0; i < 6; i++) mbar_init(bars + 8 * (2 * i + warp - 12), 1);
        asm volatile("fence.proxy.async.shared::cta;" ::: "memory");
      }
      asm volatile("bar.sync 2, 64;" ::: "memory");
      asm volatile("bar.arrive 0, 384;" ::: "memory");
      asm volatile("bar.arrive 4, 256;" ::: "memory");
      if (lane == 0) {
        if (!helper) {
#pragma unroll 1
          for (int n = 0; n < NR; n++) { if (warp == 12) x_load(n); ring_part(warp - 12, n, n); }
        }
      }
    } else {
      if (lane != 0) {
      } else if (warp == 15) {
#pragma unroll
        for (int i = B_FT; i < NBAR; i++) mbar_init(bars + 8 * i, i < B_EA ? 1 : i < B_T ? 2 : 4);
#pragma unroll
        for (int i = 0; i < 4; i++) mbar_expect_tx(bars + 8 * (B_Z + i), U);
        asm volatile("fence.mbarrier_init.release.cluster;" ::: "memory");
        asm volatile("fence.proxy.async.shared::cta;" ::: "memory");
      } else {
#pragma unroll
        for (int i = 1; i < 4; i++) asm volatile("prefetch.tensormap [%0];" ::"l"((const char*)&maps + i * 128) : "memory");
      }
      if (lane == 0) PROF_EV(warp + 14);
      __syncwarp();
      asm volatile("bar.arrive 0, 384;" ::: "memory");
      asm volatile("bar.arrive 4, 256;" ::: "memory");
    }
    __syncwarp();
    asm volatile("barrier.cluster.arrive.relaxed.aligned;" ::: "memory");
    asm volatile("bar.sync 3, 128;" ::: "memory");
    if (lane == 0 && (!helper || warp == 15)) {
      if (warp < 14) {
        if (warp == 12) x_load(NR);
        int slot = 0, par = 0;
#pragma unroll 1
        for (int n = NR; n < 32; n++) {
          mbar_wait(bars + 8 * (B_EA + slot), par);
          ring_part(warp - 12, n, slot);
          if (warp == 12 && n < 7) x_load(n + 1);
          if (++slot == NR) { slot = 0; par ^= 1; }
        }
      } else if (warp == 15) {
        const unsigned ep1 = ld_x1(&g_epoch[blockIdx.x * 8]) + 1;
        flag_wait(&g_cntX[helper ? 0 : 32 * j], ep1 * 16u);
        PROF_EV(22);
        mbar_expect_tx(bars + 8 * B_HX, U);
        bulk_load(sb + OFF_XB, g_X + (size_t)(helper ? 128 : kg * 8 + tn) * 8192, U, bars + 8 * B_HX);
        if (!helper) {
          flag_wait(&g_cntT[32 * j], ep1 * 64u);
          PROF_EV(23);
          mbar_expect_tx(bars + 8 * B_TL, U);
          tma3d(sb + OFF_T, &maps.t, bars + 8 * B_TL, 64 * j, 0, 2 * rb);
#pragma unroll 1
          for (int i = 0; i < 3; i++) {
            mbar_wait(bars + 8 * (B_PZ + (i >> 1)), 0);
            flag_wait(&g_cntP[32 * (rb * 8 + j) + i], ep1 * 8u);
            mbar_expect_tx(bars + 8 * (B_HP + i), U);
            bulk_load(sb + i * U, g_part + (size_t)((rb * 8 + j) * 3 + i) * 1024, U, bars + 8 * (B_HP + i));
          }
        }
      } else {
#pragma unroll 1
        for (int h2 = 0; h2 < 2; h2++) {
          const int s0 = 2 * rb + h2, sg = (s0 & ~6) | ((s0 & 2) << 1) | ((s0 & 4) >> 1);
          mbar_wait(bars + 8 * (B_XS + h2), 0);
#pragma unroll 1
          for (int c = 0; c < 2; c++) {
            asm volatile("cp.async.bulk.tensor.4d.global.shared::cta.bulk_group [%0, {%2, %3, %4, %5}], [%1];" ::"l"(&maps.xs),
                         "r"(sb + OFF_XB + h2 * 8192 + c * 4096), "r"(0), "r"(sg), "r"(0), "r"(16 * j + 8 * c) : "memory");
            if (j == 0)
              asm volatile("cp.async.bulk.global.shared::cta.bulk_group [%0], [%1], 256;" ::"l"(g_X + 128 * 8192 + c * 4096 + sg * 128),
                           "r"(sb + OFF_SP + h2 * 512 + c * 256) : "memory");
            if (SPACE && h2 + c < 2) __nanosleep(SPACE);
          }
        }
        bulk_done_signal(&g_cntX[32 * j]);
        PROF_EV(20);
#pragma unroll 1
        for (int t = 0; t < 8; t++) {
          const int i = t < 3 ? t + 1 : t < 6 ? t - 2 : 0;
          const int col = 64 * (2 * ((q4 + i) & 3) + ((t < 3 || t == 6) ? 1 - rank : rank));
          const uint32_t fb = bars + 8 * (B_FT + (t & 3)), dst = sb + (t & 3) * TB;
          mbar_wait(bars + 8 * (B_ET + (t == 2 ? 3 : t & 3)), t >> 2);
          mbar_expect_tx(fb, TB);
          tma2d(dst, &maps.d224, fb, col, 224 * j);
          if (t < 2) mbar_wait(bars + 8 * (B_ET + t + 1), 0);
          tma2d(dst + 28672, &maps.ft, fb, col, 64 * j);
        }
      }
    }
  }
}

typedef CUresult (*EncodeFn)(CUtensorMap*, CUtensorMapDataType, cuuint32_t, void*, const cuuint64_t*, const cuuint64_t*, const cuuint32_t*,
                             const cuuint32_t*, CUtensorMapInterleave, CUtensorMapSwizzle, CUtensorMapL2promotion, CUtensorMapFloatOOBfill);

static void encode(EncodeFn f, CUtensorMap* m, const void* base, int rank, const cuuint64_t* dims, const cuuint64_t* strides, const cuuint32_t* box,
                   CUtensorMapSwizzle sw) {
  cuuint32_t es[5] = {1, 1, 1, 1, 1};
  f(m, CU_TENSOR_MAP_DATA_TYPE_BFLOAT16, rank, (void*)base, dims, strides, box, es, CU_TENSOR_MAP_INTERLEAVE_NONE, sw,
    CU_TENSOR_MAP_L2_PROMOTION_L2_128B, CU_TENSOR_MAP_FLOAT_OOB_FILL_NONE);
}

extern "C" void kernel_launch(void* const* d_in, const int* in_sizes, int n_in, void* d_out, int out_size) {
  (void)in_sizes; (void)n_in; (void)out_size;
  const __nv_bfloat16* x = (const __nv_bfloat16*)d_in[0];
  const __nv_bfloat16* w_r = (const __nv_bfloat16*)d_in[1];
  const __nv_bfloat16* w_i = (const __nv_bfloat16*)d_in[2];
  const __nv_bfloat16* Wg = (const __nv_bfloat16*)d_in[4];
  const __nv_bfloat16* Wu = (const __nv_bfloat16*)d_in[5];
  const __nv_bfloat16* Wd = (const __nv_bfloat16*)d_in[6];
  const __nv_bfloat16* gw = (const __nv_bfloat16*)d_in[7];

  void* fp = nullptr; cudaDriverEntryPointQueryResult qr;
  cudaGetDriverEntryPoint("cuTensorMapEncodeTiled", &fp, cudaEnableDefault, &qr);
  EncodeFn enc = (EncodeFn)fp;
  void *pFT, *pET, *pX, *pT;
  cudaGetSymbolAddress(&pX, g_X); cudaGetSymbolAddress(&pT, g_T);
  cudaGetSymbolAddress(&pFT, g_FT); cudaGetSymbolAddress(&pET, g_ET);

  Maps mp;
  const CUtensorMapSwizzle S128 = CU_TENSOR_MAP_SWIZZLE_128B, S64 = CU_TENSOR_MAP_SWIZZLE_64B;
  { cuuint64_t d[3] = {512, 64, 32}, s[2] = {32768, 1024}; cuuint32_t b[3] = {64, 64, 2}; encode(enc, &mp.x, x, 3, d, s, b, S128); }
  { cuuint64_t d[2] = {512, 512}, s[1] = {1024}; cuuint32_t b[2] = {64, 64}; encode(enc, &mp.ft, pFT, 2, d, s, b, S128); }
  { cuuint64_t d[4] = {128, 32, 2, 129}, s[3] = {256, 8192, 16384}; cuuint32_t b[4] = {128, 1, 2, 8}; encode(enc, &mp.xs, pX, 4, d, s, b, CU_TENSOR_MAP_SWIZZLE_NONE); }
  { cuuint64_t d[3] = {512, 32, 64}, s[2] = {65536, 1024}; cuuint32_t b[3] = {32, 32, 2}; encode(enc, &mp.ts, pT, 3, d, s, b, S64); }
  { cuuint64_t d[3] = {512, 64, 32}, s[2] = {1024, 65536}; cuuint32_t b[3] = {64, 64, 2}; encode(enc, &mp.t, pT, 3, d, s, b, S128); }
  { cuuint64_t d[4] = {64, 64, 2, 32}, s[3] = {8192, 128, 256}; cuuint32_t b[4] = {64, 64, 2, 1}; encode(enc, &mp.e, pET, 4, d, s, b, S128); }
  { cuuint64_t d[2] = {1792, 512}, s[1] = {3584}; cuuint32_t b[2] = {64, 64}, b2[2] = {32, 128};
    encode(enc, &mp.g64, Wg, 2, d, s, b, S128); encode(enc, &mp.u64, Wu, 2, d, s, b, S128);
    encode(enc, &mp.g32, Wg, 2, d, s, b2, S64); encode(enc, &mp.u32, Wu, 2, d, s, b2, S64); }
  { cuuint64_t d[2] = {512, 1792}, s[1] = {1024}; cuuint32_t b[2] = {64, 224}; encode(enc, &mp.d224, Wd, 2, d, s, b, S128); }
  { cuuint64_t d[4] = {264, 32, 8, 8}, s[3] = {32896, 512, 4112}; cuuint32_t b[4] = {24, 32, 2, 1};
    encode(enc, &mp.wr, w_r, 4, d, s, b, CU_TENSOR_MAP_SWIZZLE_NONE); encode(enc, &mp.wi, w_i, 4, d, s, b, CU_TENSOR_MAP_SWIZZLE_NONE); }

  cudaFuncSetAttribute(fused_kernel, cudaFuncAttributeMaxDynamicSharedMemorySize, SMEM_BYTES);
  fused_kernel<<<NCTA, 512, SMEM_BYTES>>>(mp, x, w_r, w_i, gw, (__nv_bfloat16*)d_out);
}
```

```cpp
#include <cuda_runtime.h>
#include <cuda_bf16.h>
#include <cuda.h>
#include <stdint.h>

namespace tbl {
constexpr double PI = 3.14159265358979323846264338327950288;
constexpr double sin_s(double x) { double t = x, s = x; for (int n = 1; n < 12; n++) { t *= -x * x / ((2 * n) * (2 * n + 1)); s += t; } return s; }
constexpr double cos_s(double x) { double t = 1, s = 1; for (int n = 1; n < 12; n++) { t *= -x * x / ((2 * n - 1) * (2 * n)); s += t; } return s; }
constexpr double cos2048(int m) {
  m &= 2047; if (m > 1024) m = 2048 - m;
  bool neg = false; if (m > 512) { m = 1024 - m; neg = true; }
  double v = (m <= 256) ? cos_s(2 * PI * m / 2048) : sin_s(2 * PI * (512 - m) / 2048);
  return neg ? -v : v;
}
constexpr uint16_t to_bf16(double v) {
  if (v == 0) return 0;
  uint16_t s = 0; if (v < 0) { s = 0x8000; v = -v; }
  int e = 0; while (v >= 2) { v /= 2; e++; } while (v < 1) { v *= 2; e--; }
  double m = (v - 1) * 128; int mi = (int)m; double fr = m - mi;
  if (fr > 0.5 || (fr == 0.5 && (mi & 1))) mi++;
  if (mi == 128) { mi = 0; e++; }
  return (uint16_t)(s | ((e + 127) << 7) | mi);
}
struct CosT { uint16_t v[2048]; constexpr CosT() : v() { for (int i = 0; i < 2048; i++) v[i] = to_bf16(cos2048(i)); } };
struct alignas(1024) FT {
  uint16_t v[512 * 512];
  constexpr FT() : v() {
    CosT c;
    for (int r = 0; r < 512; r++) {
      int k = (r >> 4) * 8 + (r & 7), e = (r >> 3) & 1;
      int mul = 4 * k, add = e ? 512 : 0;
      if (k == 0 && e == 1) { mul = 1024; add = 0; }
      for (int d = 0; d < 512; d++) v[r * 512 + d] = c.v[(d * mul + add) & 2047];
    }
  }
};
struct alignas(1024) ET {
  uint16_t v[2048 * 128];
  constexpr ET() : v() {
    CosT c;
    for (int s = 0; s < 2048; s++)
      for (int j = 0; j < 64; j++) { v[s * 128 + j] = c.v[(s * j) & 2047]; v[s * 128 + 64 + j] = c.v[(s * j + 512) & 2047]; }
  }
};
struct alignas(1024) DT {
  uint16_t v[64 * 64];
  constexpr DT() : v() {
    CosT c;
    for (int r = 0; r < 64; r++)
      for (int n = 0; n < 64; n++) {
        const int sg = r >> 1, s0 = (sg & ~6) | ((sg & 2) << 1) | ((sg & 4) >> 1), e = r & 1, f = n & 1;
        const int m = 64 * s0 * (n >> 1) + (e == f ? 0 : e ? -512 : 512);
        v[r * 64 + (((n >> 3) ^ (r & 7)) << 3) + (n & 7)] = c.v[m & 2047];
      }
  }
};
}

__device__ constexpr tbl::FT g_FT = tbl::FT();
__device__ constexpr tbl::ET g_ET = tbl::ET();
__device__ constexpr tbl::DT g_DT = tbl::DT();

__device__ __align__(1024) uint16_t g_X[129 * 8192];
__device__ __align__(1024) uint16_t g_T[32 * 64 * 512];
__device__ __align__(1024) uint2 g_Ts[32 * 64];
__device__ __align__(1024) uint4 g_part[128 * 3 * 1024];
__device__ __align__(16) float g_gate[16 * 128];
__device__ __align__(16) uint2 g_Wh[2 * 2048];
__device__ unsigned g_epoch[132 * 8];
__device__ unsigned g_cntX[8 * 32], g_cntT[8 * 32], g_cntP[128 * 32], g_cntW[32], g_cntH[32];
#define PROF_EV(i) do {} while (0)
#define PROF_CK(i) do {} while (0)

__device__ __forceinline__ uint32_t smem_u32(const void* p) { return (uint32_t)__cvta_generic_to_shared(p); }
__device__ __forceinline__ void mbar_init(uint32_t bar, uint32_t cnt) { asm volatile("mbarrier.init.shared::cta.b64 [%0], %1;" ::"r"(bar), "r"(cnt)); }
__device__ __forceinline__ void mbar_expect_tx(uint32_t bar, uint32_t bytes) { asm volatile("mbarrier.arrive.expect_tx.shared::cta.b64 _, [%0], %1;" ::"r"(bar), "r"(bytes) : "memory"); }
__device__ __forceinline__ void mbar_arrive(uint32_t bar) { asm volatile("mbarrier.arrive.shared::cta.b64 _, [%0];" ::"r"(bar) : "memory"); }
__device__ __forceinline__ void mbar_arrive_if(bool p, uint32_t bar) {
  asm volatile("{\n.reg .pred p;\nsetp.ne.b32 p, %1, 0;\n@p mbarrier.arrive.shared::cta.b64 _, [%0];\n}" ::"r"(bar), "r"((int)p) : "memory");
}
__device__ __forceinline__ void hint_add_if(bool p, unsigned* a) {
  asm volatile("{\n.reg .pred p;\nsetp.ne.b32 p, %1, 0;\n@p red.relaxed.gpu.global.add.u32 [%0], 1;\n}" ::"l"(a), "r"((int)p) : "memory");
}
__device__ __forceinline__ void mbar_wait(uint32_t bar, uint32_t parity) {
  asm volatile(
      "{\n.reg .pred p;\n.reg .u32 n;\nmov.u32 n, 0;\n"
      "W_LOOP:\nmbarrier.try_wait.parity.shared::cta.b64 p, [%0], %1;\n@p bra W_DONE;\n"
      "add.u32 n, n, 1;\nsetp.lt.u32 p, n, 0x40000;\n@p bra W_LOOP;\ntrap;\nW_DONE:\n}" ::"r"(bar), "r"(parity) : "memory");
}
__device__ __forceinline__ void bulk_load(uint32_t dst, const void* src, uint32_t bytes, uint32_t bar) {
  asm volatile("cp.async.bulk.shared::cluster.global.mbarrier::complete_tx::bytes [%0], [%1], %2, [%3];" ::"r"(dst), "l"(src), "r"(bytes), "r"(bar) : "memory");
}
__device__ __forceinline__ void cp16(uint32_t dst, const void* src) { asm volatile("cp.async.cg.shared.global [%0], [%1], 16;" ::"r"(dst), "l"(src) : "memory"); }
__device__ __forceinline__ void spin_guard(uint32_t t0) { if ((uint32_t)clock() - t0 > (1u << 30)) __trap(); }
__device__ __forceinline__ float tagf(float v, uint32_t tag) { return __uint_as_float((__float_as_uint(v) & ~1u) | tag); }
__device__ __forceinline__ float untag(float v) { return __uint_as_float(__float_as_uint(v) & ~1u); }
__device__ __forceinline__ void st_x2(float2* p, float a, float b) { asm volatile("st.relaxed.gpu.global.v2.f32 [%0], {%1,%2};" ::"l"(p), "f"(a), "f"(b) : "memory"); }
__device__ __forceinline__ float2 ld_x2(const float2* p) { float2 v; asm volatile("ld.relaxed.gpu.global.v2.f32 {%0,%1}, [%2];" : "=f"(v.x), "=f"(v.y) : "l"(p) : "memory"); return v; }
__device__ __forceinline__ void st_u2(uint2* p, uint32_t a, uint32_t b) { asm volatile("st.relaxed.gpu.global.v2.u32 [%0], {%1,%2};" ::"l"(p), "r"(a), "r"(b) : "memory"); }
__device__ __forceinline__ void prefetch2d(const CUtensorMap* m, int c0, int c1) { asm volatile("cp.async.bulk.prefetch.tensor.2d.L2.global [%0, {%1, %2}];" ::"l"(m), "r"(c0), "r"(c1) : "memory"); }
__device__ __forceinline__ void prefetch1d(const void* p, uint32_t bytes) { asm volatile("cp.async.bulk.prefetch.L2.global [%0], %1;" ::"l"(p), "r"(bytes) : "memory"); }
__device__ __forceinline__ uint32_t ld_x1(const void* p) { uint32_t v; asm volatile("ld.relaxed.gpu.global.u32 %0, [%1];" : "=r"(v) : "l"(p) : "memory"); return v; }
__device__ __forceinline__ uint4 ld_x4(const void* p) { uint4 v; asm volatile("ld.relaxed.gpu.global.v4.u32 {%0,%1,%2,%3}, [%4];" : "=r"(v.x), "=r"(v.y), "=r"(v.z), "=r"(v.w) : "l"(p) : "memory"); return v; }
__device__ __forceinline__ void st_x4(void* p, uint32_t a, uint32_t b, uint32_t c, uint32_t d) { asm volatile("st.relaxed.gpu.global.v4.u32 [%0], {%1,%2,%3,%4};" ::"l"(p), "r"(a), "r"(b), "r"(c), "r"(d) : "memory"); }
__device__ __forceinline__ uint32_t mapa(uint32_t a, uint32_t cta) { uint32_t r; asm volatile("mapa.shared::cluster.u32 %0, %1, %2;" : "=r"(r) : "r"(a), "r"(cta)); return r; }
__device__ __forceinline__ void stsm4t(uint32_t a, uint32_t r0, uint32_t r1, uint32_t r2, uint32_t r3) {
  asm volatile("stmatrix.sync.aligned.m8n8.x4.trans.shared.b16 [%0], {%1,%2,%3,%4};" ::"r"(a), "r"(r0), "r"(r1), "r"(r2), "r"(r3) : "memory");
}
__device__ __forceinline__ void hint_add(unsigned* p) { asm volatile("red.relaxed.gpu.global.add.u32 [%0], 1;" ::"l"(p) : "memory"); }
__device__ __forceinline__ void hint_wait(const unsigned* p, unsigned target) {
  const uint32_t t0 = (uint32_t)clock();
  while ((int)(ld_x1(p) - target) < 0) spin_guard(t0);
}
__device__ __forceinline__ void bulk_done_signal(unsigned* p) {
  asm volatile("cp.async.bulk.commit_group;\ncp.async.bulk.wait_group 0;\nfence.proxy.async.global;" ::: "memory");
  hint_add(p);
}
__device__ __forceinline__ void flag_wait(const unsigned* p, unsigned target) {
  hint_wait(p, target);
  asm volatile("fence.proxy.async.global;" ::: "memory");
}
__device__ __forceinline__ void tma2d(uint32_t dst, const CUtensorMap* m, uint32_t bar, int c0, int c1) {
  asm volatile("cp.async.bulk.tensor.2d.shared::cluster.global.mbarrier::complete_tx::bytes [%0], [%1, {%3, %4}], [%2];" ::"r"(dst), "l"(m), "r"(bar), "r"(c0), "r"(c1) : "memory");
}
__device__ __forceinline__ void tma3d(uint32_t dst, const CUtensorMap* m, uint32_t bar, int c0, int c1, int c2) {
  asm volatile("cp.async.bulk.tensor.3d.shared::cluster.global.mbarrier::complete_tx::bytes [%0], [%1, {%3, %4, %5}], [%2];" ::"r"(dst), "l"(m), "r"(bar), "r"(c0), "r"(c1), "r"(c2) : "memory");
}
__device__ __forceinline__ void tma4d(uint32_t dst, const CUtensorMap* m, uint32_t bar, int c0, int c1, int c2, int c3) {
  asm volatile("cp.async.bulk.tensor.4d.shared::cluster.global.mbarrier::complete_tx::bytes [%0], [%1, {%3, %4, %5, %6}], [%2];" ::"r"(dst), "l"(m), "r"(bar), "r"(c0), "r"(c1), "r"(c2), "r"(c3) : "memory");
}
__device__ __forceinline__ void wg_fence() { asm volatile("wgmma.fence.sync.aligned;" ::: "memory"); }
__device__ __forceinline__ void wg_commit() { asm volatile("wgmma.commit_group.sync.aligned;" ::: "memory"); }
template <int N> __device__ __forceinline__ void wg_wait() { asm volatile("wgmma.wait_group.sync.aligned %0;" ::"n"(N) : "memory"); }
template <int O, int N, int NN> __device__ __forceinline__ void fence_regs(float (&d)[NN]) {
#pragma unroll
  for (int i = 0; i < N; i++) asm volatile("" : "+f"(d[O + i])::"memory");
}
__device__ __forceinline__ uint32_t pack_bf16(float lo, float hi) {
  uint32_t r; asm("cvt.rn.bf16x2.f32 %0, %1, %2;" : "=r"(r) : "f"(hi), "f"(lo)); return r;
}
__device__ __forceinline__ uint32_t pack_pin(float lo, float hi) {
  uint32_t r; asm volatile("cvt.rn.bf16x2.f32 %0, %1, %2;" : "=r"(r) : "f"(hi), "f"(lo) : "memory"); return r;
}
__device__ __forceinline__ float bf_lo(uint32_t u) { return __uint_as_float(u << 16); }
__device__ __forceinline__ float bf_hi(uint32_t u) { return __uint_as_float(u & 0xffff0000u); }

__device__ __forceinline__ uint64_t d128(uint32_t lo) { uint64_t d; asm("mov.b64 %0, {%1, 0x40000040};" : "=l"(d) : "r"(lo)); return d; }
__device__ __forceinline__ uint64_t d64(uint32_t lo) { uint64_t d; asm("mov.b64 %0, {%1, 0x80000020};" : "=l"(d) : "r"(lo)); return d; }
template<int O,int TB,int ACC,int NN> __device__ __forceinline__ void mma_ss64(float (&d)[NN], uint64_t da, uint64_t db, int sd = 0){
  if constexpr (ACC == 1) asm volatile("wgmma.mma_async.sync.aligned.m64n64k16.f32.bf16.bf16 {%0,%1,%2,%3,%4,%5,%6,%7,%8,%9,%10,%11,%12,%13,%14,%15,%16,%17,%18,%19,%20,%21,%22,%23,%24,%25,%26,%27,%28,%29,%30,%31}, %32, %33, 1, 1, 1, %35, %34;"
   : "+f"(d[O+0]), "+f"(d[O+1]), "+f"(d[O+2]), "+f"(d[O+3]), "+f"(d[O+4]), "+f"(d[O+5]), "+f"(d[O+6]), "+f"(d[O+7]), "+f"(d[O+8]), "+f"(d[O+9]), "+f"(d[O+10]), "+f"(d[O+11]), "+f"(d[O+12]), "+f"(d[O+13]), "+f"(d[O+14]), "+f"(d[O+15]), "+f"(d[O+16]), "+f"(d[O+17]), "+f"(d[O+18]), "+f"(d[O+19]), "+f"(d[O+20]), "+f"(d[O+21]), "+f"(d[O+22]), "+f"(d[O+23]), "+f"(d[O+24]), "+f"(d[O+25]), "+f"(d[O+26]), "+f"(d[O+27]), "+f"(d[O+28]), "+f"(d[O+29]), "+f"(d[O+30]), "+f"(d[O+31])
   : "l"(da), "l"(db), "n"(TB & 1), "n"(TB >> 1));
  else if constexpr (ACC == 0) asm volatile("wgmma.mma_async.sync.aligned.m64n64k16.f32.bf16.bf16 {%0,%1,%2,%3,%4,%5,%6,%7,%8,%9,%10,%11,%12,%13,%14,%15,%16,%17,%18,%19,%20,%21,%22,%23,%24,%25,%26,%27,%28,%29,%30,%31}, %32, %33, 0, 1, 1, %35, %34;"
   : "=f"(d[O+0]), "=f"(d[O+1]), "=f"(d[O+2]), "=f"(d[O+3]), "=f"(d[O+4]), "=f"(d[O+5]), "=f"(d[O+6]), "=f"(d[O+7]), "=f"(d[O+8]), "=f"(d[O+9]), "=f"(d[O+10]), "=f"(d[O+11]), "=f"(d[O+12]), "=f"(d[O+13]), "=f"(d[O+14]), "=f"(d[O+15]), "=f"(d[O+16]), "=f"(d[O+17]), "=f"(d[O+18]), "=f"(d[O+19]), "=f"(d[O+20]), "=f"(d[O+21]), "=f"(d[O+22]), "=f"(d[O+23]), "=f"(d[O+24]), "=f"(d[O+25]), "=f"(d[O+26]), "=f"(d[O+27]), "=f"(d[O+28]), "=f"(d[O+29]), "=f"(d[O+30]), "=f"(d[O+31])
   : "l"(da), "l"(db), "n"(TB & 1), "n"(TB >> 1));
  else asm volatile("{\n.reg .pred p;\nsetp.ne.b32 p, %36, 0;\nwgmma.mma_async.sync.aligned.m64n64k16.f32.bf16.bf16 {%0,%1,%2,%3,%4,%5,%6,%7,%8,%9,%10,%11,%12,%13,%14,%15,%16,%17,%18,%19,%20,%21,%22,%23,%24,%25,%26,%27,%28,%29,%30,%31}, %32, %33, p, 1, 1, %35, %34;\n}"
   : "+f"(d[O+0]), "+f"(d[O+1]), "+f"(d[O+2]), "+f"(d[O+3]), "+f"(d[O+4]), "+f"(d[O+5]), "+f"(d[O+6]), "+f"(d[O+7]), "+f"(d[O+8]), "+f"(d[O+9]), "+f"(d[O+10]), "+f"(d[O+11]), "+f"(d[O+12]), "+f"(d[O+13]), "+f"(d[O+14]), "+f"(d[O+15]), "+f"(d[O+16]), "+f"(d[O+17]), "+f"(d[O+18]), "+f"(d[O+19]), "+f"(d[O+20]), "+f"(d[O+21]), "+f"(d[O+22]), "+f"(d[O+23]), "+f"(d[O+24]), "+f"(d[O+25]), "+f"(d[O+26]), "+f"(d[O+27]), "+f"(d[O+28]), "+f"(d[O+29]), "+f"(d[O+30]), "+f"(d[O+31])
   : "l"(da), "l"(db), "n"(TB & 1), "n"(TB >> 1), "r"(sd));
}
template<int O,int TB,int ACC,int NN> __device__ __forceinline__ void mma_rs64(float (&d)[NN], uint32_t a0, uint32_t a1, uint32_t a2, uint32_t a3, uint64_t db, int sd = 0){
  if constexpr (ACC == 1) asm volatile("wgmma.mma_async.sync.aligned.m64n64k16.f32.bf16.bf16 {%0,%1,%2,%3,%4,%5,%6,%7,%8,%9,%10,%11,%12,%13,%14,%15,%16,%17,%18,%19,%20,%21,%22,%23,%24,%25,%26,%27,%28,%29,%30,%31}, {%32,%33,%34,%35}, %36, 1, 1, 1, %37;"
   : "+f"(d[O+0]), "+f"(d[O+1]), "+f"(d[O+2]), "+f"(d[O+3]), "+f"(d[O+4]), "+f"(d[O+5]), "+f"(d[O+6]), "+f"(d[O+7]), "+f"(d[O+8]), "+f"(d[O+9]), "+f"(d[O+10]), "+f"(d[O+11]), "+f"(d[O+12]), "+f"(d[O+13]), "+f"(d[O+14]), "+f"(d[O+15]), "+f"(d[O+16]), "+f"(d[O+17]), "+f"(d[O+18]), "+f"(d[O+19]), "+f"(d[O+20]), "+f"(d[O+21]), "+f"(d[O+22]), "+f"(d[O+23]), "+f"(d[O+24]), "+f"(d[O+25]), "+f"(d[O+26]), "+f"(d[O+27]), "+f"(d[O+28]), "+f"(d[O+29]), "+f"(d[O+30]), "+f"(d[O+31])
   : "r"(a0), "r"(a1), "r"(a2), "r"(a3), "l"(db), "n"(TB));
  else if constexpr (ACC == 0) asm volatile("wgmma.mma_async.sync.aligned.m64n64k16.f32.bf16.bf16 {%0,%1,%2,%3,%4,%5,%6,%7,%8,%9,%10,%11,%12,%13,%14,%15,%16,%17,%18,%19,%20,%21,%22,%23,%24,%25,%26,%27,%28,%29,%30,%31}, {%32,%33,%34,%35}, %36, 0, 1, 1, %37;"
   : "=f"(d[O+0]), "=f"(d[O+1]), "=f"(d[O+2]), "=f"(d[O+3]), "=f"(d[O+4]), "=f"(d[O+5]), "=f"(d[O+6]), "=f"(d[O+7]), "=f"(d[O+8]), "=f"(d[O+9]), "=f"(d[O+10]), "=f"(d[O+11]), "=f"(d[O+12]), "=f"(d[O+13]), "=f"(d[O+14]), "=f"(d[O+15]), "=f"(d[O+16]), "=f"(d[O+17]), "=f"(d[O+18]), "=f"(d[O+19]), "=f"(d[O+20]), "=f"(d[O+21]), "=f"(d[O+22]), "=f"(d[O+23]), "=f"(d[O+24]), "=f"(d[O+25]), "=f"(d[O+26]), "=f"(d[O+27]), "=f"(d[O+28]), "=f"(d[O+29]), "=f"(d[O+30]), "=f"(d[O+31])
   : "r"(a0), "r"(a1), "r"(a2), "r"(a3), "l"(db), "n"(TB));
  else asm volatile("{\n.reg .pred p;\nsetp.ne.b32 p, %38, 0;\nwgmma.mma_async.sync.aligned.m64n64k16.f32.bf16.bf16 {%0,%1,%2,%3,%4,%5,%6,%7,%8,%9,%10,%11,%12,%13,%14,%15,%16,%17,%18,%19,%20,%21,%22,%23,%24,%25,%26,%27,%28,%29,%30,%31}, {%32,%33,%34,%35}, %36, p, 1, 1, %37;\n}"
   : "+f"(d[O+0]), "+f"(d[O+1]), "+f"(d[O+2]), "+f"(d[O+3]), "+f"(d[O+4]), "+f"(d[O+5]), "+f"(d[O+6]), "+f"(d[O+7]), "+f"(d[O+8]), "+f"(d[O+9]), "+f"(d[O+10]), "+f"(d[O+11]), "+f"(d[O+12]), "+f"(d[O+13]), "+f"(d[O+14]), "+f"(d[O+15]), "+f"(d[O+16]), "+f"(d[O+17]), "+f"(d[O+18]), "+f"(d[O+19]), "+f"(d[O+20]), "+f"(d[O+21]), "+f"(d[O+22]), "+f"(d[O+23]), "+f"(d[O+24]), "+f"(d[O+25]), "+f"(d[O+26]), "+f"(d[O+27]), "+f"(d[O+28]), "+f"(d[O+29]), "+f"(d[O+30]), "+f"(d[O+31])
   : "r"(a0), "r"(a1), "r"(a2), "r"(a3), "l"(db), "n"(TB), "r"(sd));
}
template<int O,int TB,int ACC,int NN> __device__ __forceinline__ void mma_ss128(float (&d)[NN], uint64_t da, uint64_t db, int sd = 0){
  if constexpr (ACC == 1) asm volatile("wgmma.mma_async.sync.aligned.m64n128k16.f32.bf16.bf16 {%0,%1,%2,%3,%4,%5,%6,%7,%8,%9,%10,%11,%12,%13,%14,%15,%16,%17,%18,%19,%20,%21,%22,%23,%24,%25,%26,%27,%28,%29,%30,%31,%32,%33,%34,%35,%36,%37,%38,%39,%40,%41,%42,%43,%44,%45,%46,%47,%48,%49,%50,%51,%52,%53,%54,%55,%56,%57,%58,%59,%60,%61,%62,%63}, %64, %65, 1, 1, 1, %67, %66;"
   : "+f"(d[O+0]), "+f"(d[O+1]), "+f"(d[O+2]), "+f"(d[O+3]), "+f"(d[O+4]), "+f"(d[O+5]), "+f"(d[O+6]), "+f"(d[O+7]), "+f"(d[O+8]), "+f"(d[O+9]), "+f"(d[O+10]), "+f"(d[O+11]), "+f"(d[O+12]), "+f"(d[O+13]), "+f"(d[O+14]), "+f"(d[O+15]), "+f"(d[O+16]), "+f"(d[O+17]), "+f"(d[O+18]), "+f"(d[O+19]), "+f"(d[O+20]), "+f"(d[O+21]), "+f"(d[O+22]), "+f"(d[O+23]), "+f"(d[O+24]), "+f"(d[O+25]), "+f"(d[O+26]), "+f"(d[O+27]), "+f"(d[O+28]), "+f"(d[O+29]), "+f"(d[O+30]), "+f"(d[O+31]), "+f"(d[O+32]), "+f"(d[O+33]), "+f"(d[O+34]), "+f"(d[O+35]), "+f"(d[O+36]), "+f"(d[O+37]), "+f"(d[O+38]), "+f"(d[O+39]), "+f"(d[O+40]), "+f"(d[O+41]), "+f"(d[O+42]), "+f"(d[O+43]), "+f"(d[O+44]), "+f"(d[O+45]), "+f"(d[O+46]), "+f"(d[O+47]), "+f"(d[O+48]), "+f"(d[O+49]), "+f"(d[O+50]), "+f"(d[O+51]), "+f"(d[O+52]), "+f"(d[O+53]), "+f"(d[O+54]), "+f"(d[O+55]), "+f"(d[O+56]), "+f"(d[O+57]), "+f"(d[O+58]), "+f"(d[O+59]), "+f"(d[O+60]), "+f"(d[O+61]), "+f"(d[O+62]), "+f"(d[O+63])
   : "l"(da), "l"(db), "n"(TB & 1), "n"(TB >> 1));
  else if constexpr (ACC == 0) asm volatile("wgmma.mma_async.sync.aligned.m64n128k16.f32.bf16.bf16 {%0,%1,%2,%3,%4,%5,%6,%7,%8,%9,%10,%11,%12,%13,%14,%15,%16,%17,%18,%19,%20,%21,%22,%23,%24,%25,%26,%27,%28,%29,%30,%31,%32,%33,%34,%35,%36,%37,%38,%39,%40,%41,%42,%43,%44,%45,%46,%47,%48,%49,%50,%51,%52,%53,%54,%55,%56,%57,%58,%59,%60,%61,%62,%63}, %64, %65, 0, 1, 1, %67, %66;"
   : "=f"(d[O+0]), "=f"(d[O+1]), "=f"(d[O+2]), "=f"(d[O+3]), "=f"(d[O+4]), "=f"(d[O+5]), "=f"(d[O+6]), "=f"(d[O+7]), "=f"(d[O+8]), "=f"(d[O+9]), "=f"(d[O+10]), "=f"(d[O+11]), "=f"(d[O+12]), "=f"(d[O+13]), "=f"(d[O+14]), "=f"(d[O+15]), "=f"(d[O+16]), "=f"(d[O+17]), "=f"(d[O+18]), "=f"(d[O+19]), "=f"(d[O+20]), "=f"(d[O+21]), "=f"(d[O+22]), "=f"(d[O+23]), "=f"(d[O+24]), "=f"(d[O+25]), "=f"(d[O+26]), "=f"(d[O+27]), "=f"(d[O+28]), "=f"(d[O+29]), "=f"(d[O+30]), "=f"(d[O+31]), "=f"(d[O+32]), "=f"(d[O+33]), "=f"(d[O+34]), "=f"(d[O+35]), "=f"(d[O+36]), "=f"(d[O+37]), "=f"(d[O+38]), "=f"(d[O+39]), "=f"(d[O+40]), "=f"(d[O+41]), "=f"(d[O+42]), "=f"(d[O+43]), "=f"(d[O+44]), "=f"(d[O+45]), "=f"(d[O+46]), "=f"(d[O+47]), "=f"(d[O+48]), "=f"(d[O+49]), "=f"(d[O+50]), "=f"(d[O+51]), "=f"(d[O+52]), "=f"(d[O+53]), "=f"(d[O+54]), "=f"(d[O+55]), "=f"(d[O+56]), "=f"(d[O+57]), "=f"(d[O+58]), "=f"(d[O+59]), "=f"(d[O+60]), "=f"(d[O+61]), "=f"(d[O+62]), "=f"(d[O+63])
   : "l"(da), "l"(db), "n"(TB & 1), "n"(TB >> 1));
  else asm volatile("{\n.reg .pred p;\nsetp.ne.b32 p, %68, 0;\nwgmma.mma_async.sync.aligned.m64n128k16.f32.bf16.bf16 {%0,%1,%2,%3,%4,%5,%6,%7,%8,%9,%10,%11,%12,%13,%14,%15,%16,%17,%18,%19,%20,%21,%22,%23,%24,%25,%26,%27,%28,%29,%30,%31,%32,%33,%34,%35,%36,%37,%38,%39,%40,%41,%42,%43,%44,%45,%46,%47,%48,%49,%50,%51,%52,%53,%54,%55,%56,%57,%58,%59,%60,%61,%62,%63}, %64, %65, p, 1, 1, %67, %66;\n}"
   : "+f"(d[O+0]), "+f"(d[O+1]), "+f"(d[O+2]), "+f"(d[O+3]), "+f"(d[O+4]), "+f"(d[O+5]), "+f"(d[O+6]), "+f"(d[O+7]), "+f"(d[O+8]), "+f"(d[O+9]), "+f"(d[O+10]), "+f"(d[O+11]), "+f"(d[O+12]), "+f"(d[O+13]), "+f"(d[O+14]), "+f"(d[O+15]), "+f"(d[O+16]), "+f"(d[O+17]), "+f"(d[O+18]), "+f"(d[O+19]), "+f"(d[O+20]), "+f"(d[O+21]), "+f"(d[O+22]), "+f"(d[O+23]), "+f"(d[O+24]), "+f"(d[O+25]), "+f"(d[O+26]), "+f"(d[O+27]), "+f"(d[O+28]), "+f"(d[O+29]), "+f"(d[O+30]), "+f"(d[O+31]), "+f"(d[O+32]), "+f"(d[O+33]), "+f"(d[O+34]), "+f"(d[O+35]), "+f"(d[O+36]), "+f"(d[O+37]), "+f"(d[O+38]), "+f"(d[O+39]), "+f"(d[O+40]), "+f"(d[O+41]), "+f"(d[O+42]), "+f"(d[O+43]), "+f"(d[O+44]), "+f"(d[O+45]), "+f"(d[O+46]), "+f"(d[O+47]), "+f"(d[O+48]), "+f"(d[O+49]), "+f"(d[O+50]), "+f"(d[O+51]), "+f"(d[O+52]), "+f"(d[O+53]), "+f"(d[O+54]), "+f"(d[O+55]), "+f"(d[O+56]), "+f"(d[O+57]), "+f"(d[O+58]), "+f"(d[O+59]), "+f"(d[O+60]), "+f"(d[O+61]), "+f"(d[O+62]), "+f"(d[O+63])
   : "l"(da), "l"(db), "n"(TB & 1), "n"(TB >> 1), "r"(sd));
}
template<int O,int TB,int ACC,int NN> __device__ __forceinline__ void mma_rs128(float (&d)[NN], uint32_t a0, uint32_t a1, uint32_t a2, uint32_t a3, uint64_t db, int sd = 0){
  if constexpr (ACC == 1) asm volatile("wgmma.mma_async.sync.aligned.m64n128k16.f32.bf16.bf16 {%0,%1,%2,%3,%4,%5,%6,%7,%8,%9,%10,%11,%12,%13,%14,%15,%16,%17,%18,%19,%20,%21,%22,%23,%24,%25,%26,%27,%28,%29,%30,%31,%32,%33,%34,%35,%36,%37,%38,%39,%40,%41,%42,%43,%44,%45,%46,%47,%48,%49,%50,%51,%52,%53,%54,%55,%56,%57,%58,%59,%60,%61,%62,%63}, {%64,%65,%66,%67}, %68, 1, 1, 1, %69;"
   : "+f"(d[O+0]), "+f"(d[O+1]), "+f"(d[O+2]), "+f"(d[O+3]), "+f"(d[O+4]), "+f"(d[O+5]), "+f"(d[O+6]), "+f"(d[O+7]), "+f"(d[O+8]), "+f"(d[O+9]), "+f"(d[O+10]), "+f"(d[O+11]), "+f"(d[O+12]), "+f"(d[O+13]), "+f"(d[O+14]), "+f"(d[O+15]), "+f"(d[O+16]), "+f"(d[O+17]), "+f"(d[O+18]), "+f"(d[O+19]), "+f"(d[O+20]), "+f"(d[O+21]), "+f"(d[O+22]), "+f"(d[O+23]), "+f"(d[O+24]), "+f"(d[O+25]), "+f"(d[O+26]), "+f"(d[O+27]), "+f"(d[O+28]), "+f"(d[O+29]), "+f"(d[O+30]), "+f"(d[O+31]), "+f"(d[O+32]), "+f"(d[O+33]), "+f"(d[O+34]), "+f"(d[O+35]), "+f"(d[O+36]), "+f"(d[O+37]), "+f"(d[O+38]), "+f"(d[O+39]), "+f"(d[O+40]), "+f"(d[O+41]), "+f"(d[O+42]), "+f"(d[O+43]), "+f"(d[O+44]), "+f"(d[O+45]), "+f"(d[O+46]), "+f"(d[O+47]), "+f"(d[O+48]), "+f"(d[O+49]), "+f"(d[O+50]), "+f"(d[O+51]), "+f"(d[O+52]), "+f"(d[O+53]), "+f"(d[O+54]), "+f"(d[O+55]), "+f"(d[O+56]), "+f"(d[O+57]), "+f"(d[O+58]), "+f"(d[O+59]), "+f"(d[O+60]), "+f"(d[O+61]), "+f"(d[O+62]), "+f"(d[O+63])
   : "r"(a0), "r"(a1), "r"(a2), "r"(a3), "l"(db), "n"(TB));
  else if constexpr (ACC == 0) asm volatile("wgmma.mma_async.sync.aligned.m64n128k16.f32.bf16.bf16 {%0,%1,%2,%3,%4,%5,%6,%7,%8,%9,%10,%11,%12,%13,%14,%15,%16,%17,%18,%19,%20,%21,%22,%23,%24,%25,%26,%27,%28,%29,%30,%31,%32,%33,%34,%35,%36,%37,%38,%39,%40,%41,%42,%43,%44,%45,%46,%47,%48,%49,%50,%51,%52,%53,%54,%55,%56,%57,%58,%59,%60,%61,%62,%63}, {%64,%65,%66,%67}, %68, 0, 1, 1, %69;"
   : "=f"(d[O+0]), "=f"(d[O+1]), "=f"(d[O+2]), "=f"(d[O+3]), "=f"(d[O+4]), "=f"(d[O+5]), "=f"(d[O+6]), "=f"(d[O+7]), "=f"(d[O+8]), "=f"(d[O+9]), "=f"(d[O+10]), "=f"(d[O+11]), "=f"(d[O+12]), "=f"(d[O+13]), "=f"(d[O+14]), "=f"(d[O+15]), "=f"(d[O+16]), "=f"(d[O+17]), "=f"(d[O+18]), "=f"(d[O+19]), "=f"(d[O+20]), "=f"(d[O+21]), "=f"(d[O+22]), "=f"(d[O+23]), "=f"(d[O+24]), "=f"(d[O+25]), "=f"(d[O+26]), "=f"(d[O+27]), "=f"(d[O+28]), "=f"(d[O+29]), "=f"(d[O+30]), "=f"(d[O+31]), "=f"(d[O+32]), "=f"(d[O+33]), "=f"(d[O+34]), "=f"(d[O+35]), "=f"(d[O+36]), "=f"(d[O+37]), "=f"(d[O+38]), "=f"(d[O+39]), "=f"(d[O+40]), "=f"(d[O+41]), "=f"(d[O+42]), "=f"(d[O+43]), "=f"(d[O+44]), "=f"(d[O+45]), "=f"(d[O+46]), "=f"(d[O+47]), "=f"(d[O+48]), "=f"(d[O+49]), "=f"(d[O+50]), "=f"(d[O+51]), "=f"(d[O+52]), "=f"(d[O+53]), "=f"(d[O+54]), "=f"(d[O+55]), "=f"(d[O+56]), "=f"(d[O+57]), "=f"(d[O+58]), "=f"(d[O+59]), "=f"(d[O+60]), "=f"(d[O+61]), "=f"(d[O+62]), "=f"(d[O+63])
   : "r"(a0), "r"(a1), "r"(a2), "r"(a3), "l"(db), "n"(TB));
  else asm volatile("{\n.reg .pred p;\nsetp.ne.b32 p, %70, 0;\nwgmma.mma_async.sync.aligned.m64n128k16.f32.bf16.bf16 {%0,%1,%2,%3,%4,%5,%6,%7,%8,%9,%10,%11,%12,%13,%14,%15,%16,%17,%18,%19,%20,%21,%22,%23,%24,%25,%26,%27,%28,%29,%30,%31,%32,%33,%34,%35,%36,%37,%38,%39,%40,%41,%42,%43,%44,%45,%46,%47,%48,%49,%50,%51,%52,%53,%54,%55,%56,%57,%58,%59,%60,%61,%62,%63}, {%64,%65,%66,%67}, %68, p, 1, 1, %69;\n}"
   : "+f"(d[O+0]), "+f"(d[O+1]), "+f"(d[O+2]), "+f"(d[O+3]), "+f"(d[O+4]), "+f"(d[O+5]), "+f"(d[O+6]), "+f"(d[O+7]), "+f"(d[O+8]), "+f"(d[O+9]), "+f"(d[O+10]), "+f"(d[O+11]), "+f"(d[O+12]), "+f"(d[O+13]), "+f"(d[O+14]), "+f"(d[O+15]), "+f"(d[O+16]), "+f"(d[O+17]), "+f"(d[O+18]), "+f"(d[O+19]), "+f"(d[O+20]), "+f"(d[O+21]), "+f"(d[O+22]), "+f"(d[O+23]), "+f"(d[O+24]), "+f"(d[O+25]), "+f"(d[O+26]), "+f"(d[O+27]), "+f"(d[O+28]), "+f"(d[O+29]), "+f"(d[O+30]), "+f"(d[O+31]), "+f"(d[O+32]), "+f"(d[O+33]), "+f"(d[O+34]), "+f"(d[O+35]), "+f"(d[O+36]), "+f"(d[O+37]), "+f"(d[O+38]), "+f"(d[O+39]), "+f"(d[O+40]), "+f"(d[O+41]), "+f"(d[O+42]), "+f"(d[O+43]), "+f"(d[O+44]), "+f"(d[O+45]), "+f"(d[O+46]), "+f"(d[O+47]), "+f"(d[O+48]), "+f"(d[O+49]), "+f"(d[O+50]), "+f"(d[O+51]), "+f"(d[O+52]), "+f"(d[O+53]), "+f"(d[O+54]), "+f"(d[O+55]), "+f"(d[O+56]), "+f"(d[O+57]), "+f"(d[O+58]), "+f"(d[O+59]), "+f"(d[O+60]), "+f"(d[O+61]), "+f"(d[O+62]), "+f"(d[O+63])
   : "r"(a0), "r"(a1), "r"(a2), "r"(a3), "l"(db), "n"(TB), "r"(sd));
}

#define NEARLY 0
#define XAHEAD 3
#define HM 2
#define SPACE 100
#define WAFTER 7
#define WPACE 100
#define GATE_AT 4
#define TPACE 40
#define PFMODE 0
#define MAPMODE 0
template <int V> struct IC { static constexpr int value = V; };
struct Maps { CUtensorMap x, ft, g64, u64, e, wr, wi, xs, ts, t, g32, u32, d224; };

constexpr int NCTA = 130;
constexpr int U = 16384;
constexpr int TB = 36864;
constexpr int NR = 4;
constexpr int OFF_RING = 8 * U, OFF_Z = 9 * U, OFF_XB = 12 * U, OFF_T = 13 * U, OFF_D = OFF_T;
constexpr int OFF_BAR = 14 * U, OFF_SP = OFF_BAR + 512;
constexpr int SMEM_BYTES = OFF_SP + 1024 + 128;
constexpr int B_FX = 0, B_FA = 8, B_FT = 12, B_Z = 16, B_W = 20, B_HX = 21, B_TL = 22, B_HP = 23, B_WR = 26;
constexpr int B_EA = 30, B_ET = 34, B_PZ = 38, B_RDY = 40, B_C1 = 41;
constexpr int B_T = 42, B_XS = 43, NBAR = 45;
__host__ __device__ constexpr int rslot(int n) { return n & 3; }
__host__ __device__ constexpr int rpar(int n) { return (n >> 2) & 1; }

__global__ void __cluster_dims__(2, 1, 1) __launch_bounds__(512, 1)
fused_kernel(const __grid_constant__ Maps maps, const __nv_bfloat16* __restrict__ x, const __nv_bfloat16* __restrict__ w_r,
             const __nv_bfloat16* __restrict__ w_i, const __nv_bfloat16* __restrict__ gate_w, __nv_bfloat16* __restrict__ out) {
  extern __shared__ __align__(1024) uint8_t smem[];
  const uint32_t sb = smem_u32(smem);
  const uint32_t bars = sb + OFF_BAR;
  const int tid = threadIdx.x, lane = tid & 31;
  const int warp = __shfl_sync(0xffffffffu, tid >> 5, 0);
  const bool helper = blockIdx.x >= 128;
  const int cl = (blockIdx.x >> 1) & 63, rank = blockIdx.x & 1;
  const int q4 = cl & 3, rb = cl >> 2;
  const int j = 2 * q4 + rank;
  const int f_full = 448 * q4 + (rank ? 256 : 0);
  const int f_half = 448 * q4 + (rank ? 224 : 192);
  const int kg = 2 * j + (rb >> 3), tn = rb & 7;

  if (tid == 64) { PROF_EV(0); PROF_CK(40); }
  auto ring_part = [&](int p, int n, int slot) {
    const uint32_t fb = bars + 8 * (B_FA + slot), dst = sb + OFF_RING + slot * U + p * 8192;
    const bool table = n == 8 || n == 9 || n >= 30;
    const int q = n < 8 ? n : n - 2;
    if (p == 0) {
      mbar_expect_tx(fb, n < 8 ? U + 8192 : U);
    }
    if (table) { if (p == 0) tma4d(dst, &maps.e, fb, 0, 0, 0, 2 * rb + (n & 1)); }
    else if (n >= 26) tma2d(dst, p ? &maps.u32 : &maps.g32, fb, f_half, 128 * (n - 26));
    else {
      if (n < 8 && p == 1) tma2d(sb + OFF_XB + slot * 8192, &maps.ft, fb, 64 * n, 64 * j);
      tma2d(dst, p ? &maps.u64 : &maps.g64, fb, f_full + 64 * (q >> 3), 64 * (q & 7));
    }
  };
  auto x_load = [&](int q) {
    mbar_expect_tx(bars + 8 * (B_FX + q), U);
    tma3d(sb + q * U, &maps.x, bars + 8 * (B_FX + q), 64 * q, 0, 2 * rb);
  };
  if (warp < 8) {
    asm volatile("barrier.cluster.arrive.relaxed.aligned;" ::: "memory");
    asm volatile("setmaxnreg.inc.sync.aligned.u32 192;");
    if (tid == 0) PROF_EV(33);
    if (!helper) {
      const int wg = warp >> 2, w = warp & 3, g = lane >> 2, q = lane & 3;
      const bool elect = (tid & 127) == 0;
      float cX[32], cA[64], cB[64], ci[64], ct[64];
      const int zero = blockIdx.x >> 16;
      uint32_t h[56], yf[16];
      const uint32_t d0 = (sb & 0x3FFFF) >> 4;
      const uint32_t dK = d0 | (1u << 16), dN = d0 | (512u << 16);
      const uint32_t dX = dK + wg * 512;
      constexpr uint32_t RING = OFF_RING >> 4;
      auto waitA = [&](int n) { mbar_wait(bars + 8 * (B_FA + rslot(n)), rpar(n)); };
      auto freeA = [&](int n) { mbar_arrive_if(elect, bars + 8 * (B_EA + rslot(n))); };
      auto nop = [] {};

      if (tid == 0) PROF_EV(34);
      asm volatile("bar.sync 0, 384;" ::: "memory");
      if (tid == 0) PROF_EV(35);
#pragma unroll 1
      for (int kb = 0; kb < 8; kb++) {
        mbar_wait(bars + 8 * (B_FX + kb), 0);
        if (tid == 0 && kb == 0) PROF_EV(36);
        waitA(kb);
        wg_fence();
        const uint64_t dx = d128(dX + kb * 1024), df = d128(dK + (OFF_XB >> 4) + rslot(kb) * 512), db = d128(dN + RING + rslot(kb) * 1024);
        mma_ss64<0, 0, 2>(cX, df, dx, kb);
        mma_ss64<0, 0, 1>(cX, df + 2, dx + 2);
        wg_commit(); wg_wait<1>();
        mbar_arrive_if(elect && kb, bars + 8 * (B_EA + rslot(kb - 1)));
        mma_ss64<0, 0, 1>(cX, df + 4, dx + 4);
        mma_ss64<0, 0, 1>(cX, df + 6, dx + 6);
        wg_commit();
        mma_ss128<0, 1, 2>(cA, dx, db, kb);
#pragma unroll
        for (int k = 1; k < 4; k++) mma_ss128<0, 1, 1>(cA, dx + k * 2, db + k * 128);
        wg_commit();
        if (kb == 0 && tid == 0) PROF_EV(1);
      }
      wg_wait<1>();
      fence_regs<0, 32>(cX);
#pragma unroll
      for (int e = 0; e < 16; e++) yf[e] = pack_pin(cX[2 * e], cX[2 * e + 1]);
      if (tid == 0) PROF_EV(2);
      float o0 = 1.0f, o1 = 1.0f;
      auto glu = [&](auto scaled, auto& acc, int half, int ho, int i0, int i1) {
#pragma unroll
        for (int i = i0; i < i1; i++) {
          float a = fmaxf(acc[2 * i], 0.f) * acc[half + 2 * i], b = fmaxf(acc[2 * i + 1], 0.f) * acc[half + 1 + 2 * i];
          if (decltype(scaled)::value) { const float o = (i & 1) ? o1 : o0; a *= o; b *= o; }
          h[ho + i] = pack_pin(a, b);
        }
      };
      {
        waitA(8); waitA(9);
        const uint64_t de = d128(dN + RING + wg * 1024);
        wg_fence();
        mma_rs128<0, 1, 0>(cB, yf[0], yf[1], yf[2], yf[3], de);
#pragma unroll
        for (int k = 1; k < 4; k++) mma_rs128<0, 1, 1>(cB, yf[4 * k], yf[4 * k + 1], yf[4 * k + 2], yf[4 * k + 3], de + k * 128);
        wg_commit();
        wg_wait<1>();
        freeA(7);
        mbar_arrive_if(elect, bars + 8 * B_C1);
        fence_regs<0, 64>(cA);
        glu(IC<0>(), cA, 32, 0, 0, 16);
      }
      auto ffn_step = [&](auto first, auto split, float (&acc)[64], int n, int kb, auto done, auto work) {
        constexpr int SPLIT = decltype(split)::value;
        waitA(n);
        wg_fence();
        const uint64_t dx = d128(dX + kb * 1024), db = d128(dN + RING + rslot(n) * 1024);
        mma_ss128<0, 1, decltype(first)::value>(acc, dx, db, zero);
#pragma unroll
        for (int k = 1; k < SPLIT; k++) mma_ss128<0, 1, 1>(acc, dx + k * 2, db + k * 128);
        wg_commit();
        work();
        wg_wait<1>();
        done();
        if (SPLIT < 4) {
          wg_fence();
#pragma unroll
          for (int k = SPLIT; k < 4; k++) mma_ss128<0, 1, 1>(acc, dx + k * 2, db + k * 128);
          wg_commit();
        }
      };
      {
        const int s0 = 2 * rb + wg, kr = 2 * ((s0 & 1) | ((s0 & 4) >> 1));
        const int m = lane >> 3, r = lane & 7;
        const uint32_t a0 = sb + OFF_XB + wg * 8192 + (((w >> 1) * 8 + (m >> 1)) * 2 + (w & 1)) * 256 + (m & 1) * 128 + ((r ^ (kr + (m & 1))) << 4);
        ffn_step(IC<2>(), IC<4>(), cA, 10, 0, [&] { freeA(8); freeA(9); fence_regs<0, 64>(cB); }, nop);
#pragma unroll
        for (int i = 0; i < 4; i++)
          stsm4t(a0 + i * 1024, pack_bf16(cB[8 * i] - cB[34 + 8 * i], cB[8 * i + 1] - cB[35 + 8 * i]),
                 pack_bf16(cB[32 + 8 * i] + cB[8 * i + 2], cB[33 + 8 * i] + cB[8 * i + 3]),
                 pack_bf16(cB[8 * i + 4] - cB[38 + 8 * i], cB[8 * i + 5] - cB[39 + 8 * i]),
                 pack_bf16(cB[36 + 8 * i] + cB[8 * i + 6], cB[37 + 8 * i] + cB[8 * i + 7]));
        if (j == 0 && w == 0) {
          const uint32_t a1 = r ? sb + OFF_SP + 1024 : sb + OFF_SP + wg * 512 + (m & 1) * 256 + (m >> 1) * 128;
#pragma unroll
          for (int n = 0; n < 8; n++)
            asm volatile("stmatrix.sync.aligned.m8n8.x4.shared.b16 [%0], {%1,%2,%3,%4};" ::"r"(a1 + ((n ^ (kr + (m >> 1))) << 4)),
                         "r"(pack_bf16(cB[4 * n], cB[4 * n + 1])), "r"(pack_bf16(cB[4 * n + 2], cB[4 * n + 3])),
                         "r"(pack_bf16(cB[32 + 4 * n], cB[33 + 4 * n])), "r"(pack_bf16(cB[34 + 4 * n], cB[35 + 4 * n])) : "memory");
        }
        ffn_step(IC<1>(), IC<2>(), cA, 11, 1, [&] { freeA(10); }, [&] {
          asm volatile("fence.proxy.async.shared::cta;" ::: "memory");
          __syncwarp();
          mbar_arrive_if(lane == 0, bars + 8 * (B_XS + wg));
          if (tid == 0) PROF_EV(3);
        });
      }
      const float* gp = g_gate + rb * 128 + wg * 64 + w * 16 + g;
      uint32_t gb0 = 0, gb1 = 0, ep = 0;
#pragma unroll 1
      for (int kb = 2; kb < 8; kb++)
        ffn_step(IC<1>(), IC<1>(), cA, 10 + kb, kb, [&] {
          freeA(9 + kb);
          if (kb == 4) { gb0 = ld_x1(gp); gb1 = ld_x1(gp + 8); ep = ld_x1(&g_epoch[blockIdx.x * 8 + (tid >> 12)]); }
        }, nop);
      asm volatile("" : "+r"(ep), "+r"(gb0), "+r"(gb1)::"memory");
      const uint32_t tag = (ep + 1) & 1;
      {
        const uint32_t t0 = (uint32_t)clock();
        while (__any_sync(0xffffffffu, ((gb0 ^ tag) | (gb1 ^ tag)) & 1)) { gb0 = ld_x1(gp); gb1 = ld_x1(gp + 8); spin_guard(t0); }
      }
      const float g0 = __uint_as_float(gb0 & ~1u), g1 = __uint_as_float(gb1 & ~1u);
      o0 = 1.0f - g0; o1 = 1.0f - g1;
      ffn_step(IC<2>(), IC<1>(), cB, 18, 0, [&] { freeA(17); fence_regs<0, 64>(cA); }, [&] {
#pragma unroll
        for (int e = 0; e < 16; e++) { const float o = (e & 1) ? o1 : o0; h[e] = pack_pin(bf_lo(h[e]) * o, bf_hi(h[e]) * o); }
      });
      if (tid == 0) PROF_EV(4);
      ffn_step(IC<1>(), IC<1>(), cB, 19, 1, [&] { freeA(18); }, [&] { glu(IC<1>(), cA, 32, 16, 0, 8); });
      ffn_step(IC<1>(), IC<1>(), cB, 20, 2, [&] { freeA(19); }, [&] { glu(IC<1>(), cA, 32, 16, 8, 16); });
#pragma unroll 1
      for (int kb = 3; kb < 8; kb++) ffn_step(IC<1>(), IC<1>(), cB, 18 + kb, kb, [&] { freeA(17 + kb); }, nop);
      if (tid == 0) PROF_EV(5);
      auto m_step = [&](auto first, int i, auto done, auto work) {
        waitA(26 + i);
        wg_fence();
        const uint64_t dx = d128(dX + i * 2048), dm = d64(dN + RING + rslot(26 + i) * 1024);
        mma_ss64<0, 1, decltype(first)::value>(ct, dx, dm);
        mma_ss64<0, 1, 1>(ct, dx + 2, dm + 64);
        wg_commit();
        work();
        wg_wait<1>();
        done();
        wg_fence();
#pragma unroll
        for (int k = 2; k < 8; k++) mma_ss64<0, 1, 1>(ct, dx + ((k >> 2) * 1024 + (k & 3) * 2), dm + k * 64);
        wg_commit();
      };
      auto freeT = [&](int t) { mbar_arrive_if(elect, bars + 8 * (B_ET + t)); };
      m_step(IC<0>(), 0, [&] { freeA(25); fence_regs<0, 64>(cB); }, nop);
      m_step(IC<1>(), 1, [&] { freeA(26); freeT(0); }, [&] { glu(IC<1>(), cB, 32, 32, 0, 5); });
      m_step(IC<1>(), 2, [&] { freeA(27); freeT(1); }, [&] { glu(IC<1>(), cB, 32, 32, 5, 11); });
      m_step(IC<1>(), 3, [&] { freeT(2); }, [&] { glu(IC<1>(), cB, 32, 32, 11, 16); });
      if (wg) waitA(31); else waitA(30);
      if (tid == 0) PROF_EV(6);
      mbar_wait(bars + 8 * (j == 0 ? B_T : B_TL), 0);
      if (tid == 0) PROF_EV(7);
      wg_fence();
      {
        const uint64_t dt = d128(dN + (OFF_T >> 4) + wg * 512), de = d128(dK + RING + (2 + wg) * 1024);
        mma_ss64<0, 1, 0>(ci, de, dt);
        mma_ss64<32, 1, 0>(ci, de + 512, dt);
#pragma unroll
        for (int k = 1; k < 4; k++) {
          mma_ss64<0, 1, 1>(ci, de + k * 2, dt + k * 128);
          mma_ss64<32, 1, 1>(ci, de + (512 + k * 2), dt + k * 128);
        }
        wg_commit();
        wg_wait<1>();
        freeT(3);
        fence_regs<0, 32>(ct);
        glu(IC<1>(), ct, 16, 48, 0, 8);
      }

      auto head = [&](auto off, int t, auto first) {
        constexpr int O = decltype(off)::value;
        mbar_wait(bars + 8 * (B_FT + (t & 3)), t >> 2);
        const uint64_t db = d128(dN + (t & 3) * (TB >> 4) + rank * 256);
        wg_fence();
        mma_rs64<O, 1, decltype(first)::value>(ct, h[0], h[1], h[2], h[3], db, zero);
#pragma unroll
        for (int k = 1; k < 6; k++) mma_rs64<O, 1, 1>(ct, h[4 * k], h[4 * k + 1], h[4 * k + 2], h[4 * k + 3], db + k * 128);
        wg_commit();
        wg_wait<1>();
      };
      auto rest = [&](auto off, int t) {
        constexpr int O = decltype(off)::value;
        const uint64_t db = d128(dN + (t & 3) * (TB >> 4)), dw = db + rank * 256, dm = db + (rank ? 0 : 1536);
        wg_fence();
#pragma unroll
        for (int k = 6; k < 12; k++) mma_rs64<O, 1, 1>(ct, h[4 * k], h[4 * k + 1], h[4 * k + 2], h[4 * k + 3], dw + k * 128);
#pragma unroll
        for (int k = 0; k < 2; k++) mma_rs64<O, 1, 1>(ct, h[48 + 4 * k], h[49 + 4 * k], h[50 + 4 * k], h[51 + 4 * k], dm + k * 128);
#pragma unroll
        for (int k = 0; k < 4; k++) mma_rs64<O, 1, 1>(ct, yf[4 * k], yf[4 * k + 1], yf[4 * k + 2], yf[4 * k + 3], db + (14 + k) * 128);
        wg_commit();
      };
      const uint32_t peerZ = mapa(sb + OFF_Z + tid * 16, rank ^ 1), peerB = mapa(bars + 8 * B_Z, rank ^ 1);
      auto send = [&](auto off, int t) {
        constexpr int O = decltype(off)::value;
        fence_regs<O, 32>(ct);
        const bool grid = t >= 3 && t < 6;
        const int z = grid ? t - 3 : t == 6 ? 3 : t;
        if (grid) {
          mbar_wait(bars + 8 * (B_Z + z), 0);
#pragma unroll
          for (int i = 0; i < 4; i++) {
            const uint4 p = *(const uint4*)(smem + OFF_Z + z * U + i * 4096 + tid * 16);
            const uint32_t a[4] = {p.x, p.y, p.z, p.w};
#pragma unroll
            for (int e = 0; e < 4; e++) { ct[O + 8 * i + 2 * e] += bf_lo(a[e]); ct[O + 8 * i + 2 * e + 1] += bf_hi(a[e]); }
          }
        }
        uint32_t pk[16];
#pragma unroll
        for (int i = 0; i < 16; i++) pk[i] = pack_bf16(ct[O + 2 * i], ct[O + 2 * i + 1]);
        if (grid) {
          const int owner = rb * 8 + 2 * ((q4 + z + 1) & 3) + rank;
          uint4* dst = g_part + (size_t)(owner * 3 + z) * 1024 + tid;
#pragma unroll
          for (int i = 0; i < 4; i++) st_x4(dst + i * 256, (pk[4 * i] & ~1u) | tag, pk[4 * i + 1], pk[4 * i + 2], pk[4 * i + 3]);
          __syncwarp();
          hint_add_if(lane == 0, &g_cntP[32 * owner + z]);
        } else {
#pragma unroll
          for (int i = 0; i < 4; i++)
            asm volatile("st.async.weak.shared::cluster.mbarrier::complete_tx::bytes.v4.b32 [%0], {%1,%2,%3,%4}, [%5];" ::"r"(peerZ + z * U + i * 4096),
                         "r"(pk[4 * i]), "r"(pk[4 * i + 1]), "r"(pk[4 * i + 2]), "r"(pk[4 * i + 3]), "r"(peerB + 8 * z) : "memory");
        }
      };
      asm volatile("barrier.cluster.wait.aligned;" ::: "memory");
      head(IC<0>(), 0, IC<2>());
      if (elect) asm volatile("mbarrier.arrive.shared::cluster.b64 _, [%0];" ::"r"(mapa(bars + 8 * B_RDY, rank ^ 1)) : "memory");
      fence_regs<0, 64>(ci);
#pragma unroll
      for (int i = 0; i < 16; i++) {
        const float gg = ((i & 1) ? g1 : g0) * (2.0f / (2048.0f * 512.0f));
        if (i & 2) yf[i] = pack_pin((ci[2 * i] - ci[28 + 2 * i]) * gg, (ci[2 * i + 1] - ci[29 + 2 * i]) * gg);
        else yf[i] = pack_pin((ci[2 * i] + ci[36 + 2 * i]) * gg, (ci[2 * i + 1] + ci[37 + 2 * i]) * gg);
      }
      if (tid == 0) PROF_EV(8);
#pragma unroll 1
      for (int t = 0;; t += 2) {
        rest(IC<0>(), t);
        head(IC<32>(), t + 1, IC<2>());
        mbar_arrive_if(elect && t < 6, bars + 8 * (B_ET + t));
        if (t == 0) mbar_wait(bars + 8 * B_RDY, 0);
        send(IC<0>(), t);
        rest(IC<32>(), t + 1);
        if (t == 6) break;
        head(IC<0>(), t + 2, IC<2>());
        mbar_arrive_if(elect, bars + 8 * (B_ET + t + 1));
        send(IC<32>(), t + 1);
      }
      if (tid == 0) PROF_EV(9);
      {
        float sum[32];
        mbar_wait(bars + 8 * (B_Z + 3), 0);
#pragma unroll
        for (int i = 0; i < 4; i++) {
          const uint4 p = *(const uint4*)(smem + OFF_Z + 3 * U + i * 4096 + tid * 16);
          const uint32_t a[4] = {p.x, p.y, p.z, p.w};
#pragma unroll
          for (int e = 0; e < 4; e++) { sum[8 * i + 2 * e] = bf_lo(a[e]); sum[8 * i + 2 * e + 1] = bf_hi(a[e]); }
        }
#pragma unroll 1
        for (int z = 0; z < 3; z++) {
          mbar_wait(bars + 8 * (B_HP + z), 0);
          if (z == 2 && tid == 0) PROF_EV(24);
          uint4 pv[4];
#pragma unroll
          for (int i = 0; i < 4; i++) pv[i] = *(const uint4*)(smem + z * U + i * 4096 + tid * 16);
          const uint32_t t0 = (uint32_t)clock();
          while (__any_sync(0xffffffffu, ((pv[0].x ^ tag) | (pv[1].x ^ tag) | (pv[2].x ^ tag) | (pv[3].x ^ tag)) & 1)) {
#pragma unroll
            for (int i = 0; i < 4; i++) pv[i] = ld_x4(g_part + (size_t)((rb * 8 + j) * 3 + z) * 1024 + tid + i * 256);
            spin_guard(t0);
          }
#pragma unroll
          for (int i = 0; i < 4; i++) {
            const uint32_t a[4] = {pv[i].x & ~1u, pv[i].y, pv[i].z, pv[i].w};
#pragma unroll
            for (int e = 0; e < 4; e++) { sum[8 * i + 2 * e] += bf_lo(a[e]); sum[8 * i + 2 * e + 1] += bf_hi(a[e]); }
          }
        }
        if (tid == 0) PROF_EV(14);
        wg_wait<0>();
        fence_regs<32, 32>(ct);
#pragma unroll
        for (int i = 0; i < 32; i++) sum[i] += ct[32 + i];
        const uint32_t stg = sb + OFF_T + warp * 2048;
        const int mr = (lane & 7) + ((lane >> 3) & 1) * 8, mc = lane >> 4;
#pragma unroll
        for (int i = 0; i < 4; i++) {
          const uint32_t a = stg + mr * 128 + (((2 * i + mc) ^ (mr & 7)) << 4);
          asm volatile("stmatrix.sync.aligned.m8n8.x4.shared.b16 [%0], {%1,%2,%3,%4};" ::"r"(a), "r"(pack_bf16(sum[8 * i], sum[8 * i + 1])),
                       "r"(pack_bf16(sum[8 * i + 2], sum[8 * i + 3])), "r"(pack_bf16(sum[8 * i + 4], sum[8 * i + 5])),
                       "r"(pack_bf16(sum[8 * i + 6], sum[8 * i + 7])) : "memory");
        }
        __syncwarp();
#pragma unroll
        for (int i = 0; i < 4; i++) {
          const int r = 4 * i + (lane >> 3), c = lane & 7;
          const uint4 v = *(const uint4*)(smem + OFF_T + warp * 2048 + r * 128 + ((c ^ (r & 7)) << 4));
          *(uint4*)(out + (size_t)(2 * rb + wg + 32 * (16 * w + r)) * 512 + 64 * j + 8 * c) = v;
        }
      }
      if (tid == 0) { g_epoch[blockIdx.x * 8] = ep + 1; PROF_EV(15); PROF_CK(41); }
    }
  } else if (warp < 12) {
    asm volatile("setmaxnreg.dec.sync.aligned.u32 104;");
    asm volatile("barrier.cluster.arrive.relaxed.aligned;" ::: "memory");
    const int t = tid - 256, w = warp - 8;
    const uint32_t ep = ld_x1(&g_epoch[blockIdx.x * 8]);
    const uint32_t tag = (ep + 1) & 1;
    auto gate_rows = [&] {
      const int r = 16 * j + 4 * w + (lane >> 3);
      const uint4* px = (const uint4*)(x + (size_t)(2 * rb + (r >> 6) + 32 * (r & 63)) * 512) + (lane & 7);
      const uint4* pg = (const uint4*)gate_w + (lane & 7);
      {
        float a = 0.f;
#pragma unroll 1
        for (int i = 0; i < 8; i += 4) {
          uint4 u[4], v[4];
#pragma unroll
          for (int e = 0; e < 4; e++) { u[e] = __ldg(px + (i + e) * 8); v[e] = __ldg(pg + (i + e) * 8); }
#pragma unroll
          for (int e = 0; e < 4; e++) {
            a = fmaf(bf_lo(u[e].x), bf_lo(v[e].x), a); a = fmaf(bf_hi(u[e].x), bf_hi(v[e].x), a);
            a = fmaf(bf_lo(u[e].y), bf_lo(v[e].y), a); a = fmaf(bf_hi(u[e].y), bf_hi(v[e].y), a);
            a = fmaf(bf_lo(u[e].z), bf_lo(v[e].z), a); a = fmaf(bf_hi(u[e].z), bf_hi(v[e].z), a);
            a = fmaf(bf_lo(u[e].w), bf_lo(v[e].w), a); a = fmaf(bf_hi(u[e].w), bf_hi(v[e].w), a);
          }
        }
#pragma unroll
        for (int o = 4; o; o >>= 1) a += __shfl_xor_sync(0xffffffffu, a, o);
        if ((lane & 7) == 0)
          asm volatile("st.relaxed.gpu.global.f32 [%0], %1;" ::"l"(g_gate + rb * 128 + r), "f"(tagf(__fdividef(1.0f, 1.0f + __expf(-a)), tag)) : "memory");
        if (t == 0) PROF_EV(18);
      }
      if (w == 0) {
        const int c = lane >> 4, jj = 16 * blockIdx.x + (lane & 15), jm = (2048 - jj) & 2047;
        const unsigned short* pr = (const unsigned short*)w_r + 256 * c;
        const unsigned short* pi = (const unsigned short*)w_i + 256 * c;
        const float wr = 0.25f * (bf_lo(__ldg(pr + jj * 257)) + bf_lo(__ldg(pr + jm * 257)));
        const float wi = 0.25f * (bf_lo(__ldg(pi + jj * 257)) - bf_lo(__ldg(pi + jm * 257)));
        st_u2(g_Wh + c * 2048 + jj, c ? pack_bf16(-wi, wr) : pack_bf16(wr, wi), tag);
        __syncwarp();
        hint_add_if(lane == 0, &g_cntW[0]);
      }
    };
    {
      const int g = lane >> 2, q = lane & 3;
      uint32_t wf[32];
      if (!helper) {
        asm volatile("bar.sync 4, 256;" ::: "memory");
        mbar_wait(bars + 8 * (B_FX + GATE_AT), 0);
        gate_rows();
        const uint32_t wa = sb + OFF_T + w * (3072 + 4) + q * 48 + g * 2;
        mbar_wait(bars + 8 * B_C1, 0);
        if (t == 0) PROF_EV(32);
        __nanosleep(WPACE * w);
#pragma unroll 1
        for (int ri = 0; ri < 2; ri++) {
          if (lane == 0) {
            mbar_expect_tx(bars + 8 * (B_WR + w), 3072);
            tma4d(sb + OFF_T + w * 3072, ri ? &maps.wi : &maps.wr, bars + 8 * (B_WR + w), 16 * kg, 0, 2 * w, tn);
          }
          mbar_wait(bars + 8 * (B_WR + w), ri);
#pragma unroll
          for (int n2 = 0; n2 < 4; n2++) {
            uint32_t v[8];
#pragma unroll
            for (int i = 0; i < 8; i++)
              asm volatile("ld.shared.u16 %0, [%1];" : "=r"(v[i]) : "r"(wa + (2 * n2 + ((i >> 1) & 1)) * 192 + (i & 1) * (1536 + 2) + (i >> 2) * 16) : "memory");
#pragma unroll
            for (int i = 0; i < 8; i++) {
              uint32_t& d = wf[(i >> 2) * 16 + 4 * n2 + (i & 3)];
              d = __byte_perm(d, v[i], 0x5432);
              asm volatile("" : "+r"(d)::"memory");
            }
          }
          __syncwarp();
        }
        asm volatile("bar.sync 1, 128;" ::: "memory");
        if (t == 0) PROF_EV(11);
      } else {
        asm volatile("bar.sync 4, 256;" ::: "memory");
        hint_wait(&g_cntW[0], (ep + 1) * 128u);
        const uint32_t t0 = (uint32_t)clock();
#pragma unroll 1
        for (;;) {
          uint32_t bad = 0;
#pragma unroll
          for (int i = 0; i < 32; i++) {
            const float2 v = ld_x2((const float2*)g_Wh + (i >> 4) * 2048 + 16 * w + g + 8 * (i & 1) + 64 * q + ((i >> 1) & 7) * 256);
            wf[i] = __float_as_uint(v.x); bad |= __float_as_uint(v.y) ^ tag;
          }
          if (!__any_sync(0xffffffffu, bad & 1)) break;
          spin_guard(t0);
        }
        if (t == 0) PROF_EV(11);
      }
      if (t == 0) { mbar_expect_tx(bars + 8 * B_W, 8192); bulk_load(sb + OFF_D, g_DT.v, 8192, bars + 8 * B_W); }
      mbar_wait(bars + 8 * B_W, 0);
      mbar_wait(bars + 8 * B_HX, 0);
      if (t == 0) PROF_EV(12);
      const uint32_t dd = (sb & 0x3FFFF) >> 4;
      const uint64_t dF = d128((dd + (OFF_D >> 4)) | (512u << 16)), dI = d128((dd + (OFF_D >> 4)) | (1u << 16)), dA = d128((dd + (OFF_XB >> 4)) | (512u << 16));
      float az[32];
      const int zero = blockIdx.x >> 16;
      uint32_t pf[32];
#pragma unroll
      for (int mt = 0; mt < 2; mt++) {
        wg_fence();
        if (mt == 0) mma_ss64<0, 3, 0>(az, dA, dF);
        else mma_ss64<0, 3, 2>(az, dA + 512, dF, zero);
#pragma unroll
        for (int k = 1; k < 4; k++) mma_ss64<0, 3, 1>(az, dA + (mt * 512 + k * 128), dF + k * 128);
        wg_commit();
        wg_wait<0>();
        fence_regs<0, 32>(az);
#pragma unroll
        for (int i = 0; i < 16; i++) {
          const float wr = bf_lo(wf[16 * mt + i]), wi = bf_hi(wf[16 * mt + i]);
          pf[16 * mt + i] = pack_pin(fmaf(az[2 * i], wr, -az[2 * i + 1] * wi), fmaf(az[2 * i], wi, az[2 * i + 1] * wr));
        }
      }
      if (t == 0) PROF_EV(16);
#pragma unroll
      for (int mt = 0; mt < 2; mt++) {
        wg_fence();
        mma_rs64<0, 0, 2>(az, pf[16 * mt], pf[16 * mt + 1], pf[16 * mt + 2], pf[16 * mt + 3], dI, mt ? (int)helper : zero);
#pragma unroll
        for (int k = 1; k < 4; k++) mma_rs64<0, 0, 1>(az, pf[16 * mt + 4 * k], pf[16 * mt + 4 * k + 1], pf[16 * mt + 4 * k + 2], pf[16 * mt + 4 * k + 3], dI + k * 2);
        wg_commit();
        wg_wait<0>();
        fence_regs<0, 32>(az);
        if (!helper) {
          const int m = lane >> 3, r = lane & 7;
          const int sl = 2 * (m >> 1) + ((r >> 1) & 1) + 4 * (r >> 2);
          const uint32_t a0 = sb + OFF_XB + (2 * w + (m & 1)) * 2048 + sl * 64 + (((mt * 2 + (r & 1)) ^ (sl >> 1)) << 4);
#pragma unroll
          for (int i = 0; i < 4; i++)
            stsm4t(a0 + i * 512, pack_bf16(az[8 * i], az[8 * i + 1]), pack_bf16(az[8 * i + 2], az[8 * i + 3]), pack_bf16(az[8 * i + 4], az[8 * i + 5]),
                   pack_bf16(az[8 * i + 6], az[8 * i + 7]));
        }
      }
      if (helper) {
#pragma unroll
        for (int i = 0; i < 16; i++) {
          const int n = i >> 1, s0 = 8 * (n >> 1) + 2 * (n & 1) + (q & 1) + 4 * (q >> 1);
          if ((n & 1) == (int)(blockIdx.x & 1)) st_u2(g_Ts + s0 * 64 + 16 * w + g + 8 * (i & 1), pack_bf16(az[2 * i], az[2 * i + 1]), tag);
        }
        __syncwarp();
        hint_add_if(lane == 0, &g_cntH[0]);
        if (t == 0) { g_epoch[blockIdx.x * 8] = ep + 1; PROF_EV(13); }
      } else {
        asm volatile("fence.proxy.async.shared::cta;" ::: "memory");
        __syncwarp();
        if (lane == 0) {
          if (t == 0) PROF_EV(17);
          if (SPACE) __nanosleep(SPACE * w);
          asm volatile("cp.async.bulk.tensor.3d.global.shared::cta.bulk_group [%0, {%2, %3, %4}], [%1];" ::"l"(&maps.ts), "r"(sb + OFF_XB + w * 4096),
                       "r"(32 * kg), "r"(0), "r"(8 * tn + 2 * w) : "memory");
          bulk_done_signal(&g_cntT[32 * j]);
          if (t == 96) PROF_EV(13);
        }
        __syncwarp();
        if (j == 0) {
          hint_wait(&g_cntH[0], (ep + 1) * 8u);
          const uint32_t t0 = (uint32_t)clock();
          float2 v;
          do { v = ld_x2((const float2*)g_Ts + 2 * rb * 64 + t); spin_guard(t0); } while (__any_sync(0xffffffffu, (__float_as_uint(v.y) ^ tag) & 1));
          mbar_wait(bars + 8 * B_TL, 0);
          const uint32_t u = __float_as_uint(v.x);
          *(uint16_t*)(smem + OFF_T + t * 128 + ((t & 7) << 4)) = (uint16_t)u;
          *(uint16_t*)(smem + OFF_T + t * 128 + (((t & 7) ^ 1) << 4)) = (uint16_t)(u >> 16);
          asm volatile("fence.proxy.async.shared::cta;" ::: "memory");
          __syncwarp();
          mbar_arrive_if(lane == 0, bars + 8 * B_T);
        }
      }
    }
  } else {
    asm volatile("setmaxnreg.dec.sync.aligned.u32 24;");
    if (warp < 14) {
      if (lane == 0) {
#pragma unroll
        for (int i = 0; i < 6; i++) mbar_init(bars + 8 * (2 * i + warp - 12), 1);
        asm volatile("fence.proxy.async.shared::cta;" ::: "memory");
      }
      asm volatile("bar.sync 2, 64;" ::: "memory");
      asm volatile("bar.arrive 0, 384;" ::: "memory");
      asm volatile("bar.arrive 4, 256;" ::: "memory");
      if (lane == 0) {
        if (!helper) {
#pragma unroll 1
          for (int n = 0; n < NR; n++) { if (warp == 12) x_load(n); ring_part(warp - 12, n, n); }
        }
      }
    } else {
      if (lane != 0) {
      } else if (warp == 15) {
#pragma unroll
        for (int i = B_FT; i < NBAR; i++) mbar_init(bars + 8 * i, i < B_EA ? 1 : i < B_T ? 2 : 4);
#pragma unroll
        for (int i = 0; i < 4; i++) mbar_expect_tx(bars + 8 * (B_Z + i), U);
        asm volatile("fence.mbarrier_init.release.cluster;" ::: "memory");
        asm volatile("fence.proxy.async.shared::cta;" ::: "memory");
      } else {
#pragma unroll
        for (int i = 1; i < 4; i++) asm volatile("prefetch.tensormap [%0];" ::"l"((const char*)&maps + i * 128) : "memory");
      }
      if (lane == 0) PROF_EV(warp + 14);
      __syncwarp();
      asm volatile("bar.arrive 0, 384;" ::: "memory");
      asm volatile("bar.arrive 4, 256;" ::: "memory");
    }
    __syncwarp();
    asm volatile("barrier.cluster.arrive.relaxed.aligned;" ::: "memory");
    asm volatile("bar.sync 3, 128;" ::: "memory");
    if (lane == 0 && (!helper || warp == 15)) {
      if (warp < 14) {
        if (warp == 12) x_load(NR);
        int slot = 0, par = 0;
#pragma unroll 1
        for (int n = NR; n < 32; n++) {
          mbar_wait(bars + 8 * (B_EA + slot), par);
          ring_part(warp - 12, n, slot);
          if (warp == 12 && n < 7) x_load(n + 1);
          if (++slot == NR) { slot = 0; par ^= 1; }
        }
      } else if (warp == 15) {
        const unsigned ep1 = ld_x1(&g_epoch[blockIdx.x * 8]) + 1;
        flag_wait(&g_cntX[helper ? 0 : 32 * j], ep1 * 16u);
        PROF_EV(22);
        mbar_expect_tx(bars + 8 * B_HX, U);
        bulk_load(sb + OFF_XB, g_X + (size_t)(helper ? 128 : kg * 8 + tn) * 8192, U, bars + 8 * B_HX);
        if (!helper) {
          flag_wait(&g_cntT[32 * j], ep1 * 64u);
          PROF_EV(23);
          mbar_expect_tx(bars + 8 * B_TL, U);
          tma3d(sb + OFF_T, &maps.t, bars + 8 * B_TL, 64 * j, 0, 2 * rb);
#pragma unroll 1
          for (int i = 0; i < 3; i++) {
            mbar_wait(bars + 8 * (B_PZ + (i >> 1)), 0);
            flag_wait(&g_cntP[32 * (rb * 8 + j) + i], ep1 * 8u);
            mbar_expect_tx(bars + 8 * (B_HP + i), U);
            bulk_load(sb + i * U, g_part + (size_t)((rb * 8 + j) * 3 + i) * 1024, U, bars + 8 * (B_HP + i));
          }
        }
      } else {
#pragma unroll 1
        for (int h2 = 0; h2 < 2; h2++) {
          const int s0 = 2 * rb + h2, sg = (s0 & ~6) | ((s0 & 2) << 1) | ((s0 & 4) >> 1);
          mbar_wait(bars + 8 * (B_XS + h2), 0);
#pragma unroll 1
          for (int c = 0; c < 2; c++) {
            asm volatile("cp.async.bulk.tensor.4d.global.shared::cta.bulk_group [%0, {%2, %3, %4, %5}], [%1];" ::"l"(&maps.xs),
                         "r"(sb + OFF_XB + h2 * 8192 + c * 4096), "r"(0), "r"(sg), "r"(0), "r"(16 * j + 8 * c) : "memory");
            if (j == 0)
              asm volatile("cp.async.bulk.global.shared::cta.bulk_group [%0], [%1], 256;" ::"l"(g_X + 128 * 8192 + c * 4096 + sg * 128),
                           "r"(sb + OFF_SP + h2 * 512 + c * 256) : "memory");
            if (SPACE && h2 + c < 2) __nanosleep(SPACE);
          }
        }
        bulk_done_signal(&g_cntX[32 * j]);
        PROF_EV(20);
#pragma unroll 1
        for (int t = 0; t < 8; t++) {
          const int i = t < 3 ? t + 1 : t < 6 ? t - 2 : 0;
          const int col = 64 * (2 * ((q4 + i) & 3) + ((t < 3 || t == 6) ? 1 - rank : rank));
          const uint32_t fb = bars + 8 * (B_FT + (t & 3)), dst = sb + (t & 3) * TB;
          mbar_wait(bars + 8 * (B_ET + (t == 2 ? 3 : t & 3)), t >> 2);
          mbar_expect_tx(fb, TB);
          tma2d(dst, &maps.d224, fb, col, 224 * j);
          if (t < 2) mbar_wait(bars + 8 * (B_ET + t + 1), 0);
          tma2d(dst + 28672, &maps.ft, fb, col, 64 * j);
        }
      }
    }
  }
}

typedef CUresult (*EncodeFn)(CUtensorMap*, CUtensorMapDataType, cuuint32_t, void*, const cuuint64_t*, const cuuint64_t*, const cuuint32_t*,
                             const cuuint32_t*, CUtensorMapInterleave, CUtensorMapSwizzle, CUtensorMapL2promotion, CUtensorMapFloatOOBfill);

static void encode(EncodeFn f, CUtensorMap* m, const void* base, int rank, const cuuint64_t* dims, const cuuint64_t* strides, const cuuint32_t* box,
                   CUtensorMapSwizzle sw) {
  cuuint32_t es[5] = {1, 1, 1, 1, 1};
  f(m, CU_TENSOR_MAP_DATA_TYPE_BFLOAT16, rank, (void*)base, dims, strides, box, es, CU_TENSOR_MAP_INTERLEAVE_NONE, sw,
    CU_TENSOR_MAP_L2_PROMOTION_L2_128B, CU_TENSOR_MAP_FLOAT_OOB_FILL_NONE);
}

extern "C" void kernel_launch(void* const* d_in, const int* in_sizes, int n_in, void* d_out, int out_size) {
  (void)in_sizes; (void)n_in; (void)out_size;
  const __nv_bfloat16* x = (const __nv_bfloat16*)d_in[0];
  const __nv_bfloat16* w_r = (const __nv_bfloat16*)d_in[1];
  const __nv_bfloat16* w_i = (const __nv_bfloat16*)d_in[2];
  const __nv_bfloat16* Wg = (const __nv_bfloat16*)d_in[4];
  const __nv_bfloat16* Wu = (const __nv_bfloat16*)d_in[5];
  const __nv_bfloat16* Wd = (const __nv_bfloat16*)d_in[6];
  const __nv_bfloat16* gw = (const __nv_bfloat16*)d_in[7];

  void* fp = nullptr; cudaDriverEntryPointQueryResult qr;
  cudaGetDriverEntryPoint("cuTensorMapEncodeTiled", &fp, cudaEnableDefault, &qr);
  EncodeFn enc = (EncodeFn)fp;
  void *pFT, *pET, *pX, *pT;
  cudaGetSymbolAddress(&pX, g_X); cudaGetSymbolAddress(&pT, g_T);
  cudaGetSymbolAddress(&pFT, g_FT); cudaGetSymbolAddress(&pET, g_ET);

  Maps mp;
  const CUtensorMapSwizzle S128 = CU_TENSOR_MAP_SWIZZLE_128B, S64 = CU_TENSOR_MAP_SWIZZLE_64B;
  { cuuint64_t d[3] = {512, 64, 32}, s[2] = {32768, 1024}; cuuint32_t b[3] = {64, 64, 2}; encode(enc, &mp.x, x, 3, d, s, b, S128); }
  { cuuint64_t d[2] = {512, 512}, s[1] = {1024}; cuuint32_t b[2] = {64, 64}; encode(enc, &mp.ft, pFT, 2, d, s, b, S128); }
  { cuuint64_t d[4] = {128, 32, 2, 129}, s[3] = {256, 8192, 16384}; cuuint32_t b[4] = {128, 1, 2, 8}; encode(enc, &mp.xs, pX, 4, d, s, b, CU_TENSOR_MAP_SWIZZLE_NONE); }
  { cuuint64_t d[3] = {512, 32, 64}, s[2] = {65536, 1024}; cuuint32_t b[3] = {32, 32, 2}; encode(enc, &mp.ts, pT, 3, d, s, b, S64); }
  { cuuint64_t d[3] = {512, 64, 32}, s[2] = {1024, 65536}; cuuint32_t b[3] = {64, 64, 2}; encode(enc, &mp.t, pT, 3, d, s, b, S128); }
  { cuuint64_t d[4] = {64, 64, 2, 32}, s[3] = {8192, 128, 256}; cuuint32_t b[4] = {64, 64, 2, 1}; encode(enc, &mp.e, pET, 4, d, s, b, S128); }
  { cuuint64_t d[2] = {1792, 512}, s[1] = {3584}; cuuint32_t b[2] = {64, 64}, b2[2] = {32, 128};
    encode(enc, &mp.g64, Wg, 2, d, s, b, S128); encode(enc, &mp.u64, Wu, 2, d, s, b, S128);
    encode(enc, &mp.g32, Wg, 2, d, s, b2, S64); encode(enc, &mp.u32, Wu, 2, d, s, b2, S64); }
  { cuuint64_t d[2] = {512, 1792}, s[1] = {1024}; cuuint32_t b[2] = {64, 224}; encode(enc, &mp.d224, Wd, 2, d, s, b, S128); }
  { cuuint64_t d[4] = {264, 32, 8, 8}, s[3] = {32896, 512, 4112}; cuuint32_t b[4] = {24, 32, 2, 1};
    encode(enc, &mp.wr, w_r, 4, d, s, b, CU_TENSOR_MAP_SWIZZLE_NONE); encode(enc, &mp.wi, w_i, 4, d, s, b, CU_TENSOR_MAP_SWIZZLE_NONE); }

  cudaFuncSetAttribute(fused_kernel, cudaFuncAttributeMaxDynamicSharedMemorySize, SMEM_BYTES);
  fused_kernel<<<NCTA, 512, SMEM_BYTES>>>(mp, x, w_r, w_i, gw, (__nv_bfloat16*)d_out);
}
```

```cpp
#include <cuda_runtime.h>
#include <cuda_bf16.h>
#include <cuda.h>
#include <stdint.h>

namespace tbl {
constexpr double PI = 3.14159265358979323846264338327950288;
constexpr double sin_s(double x) { double t = x, s = x; for (int n = 1; n < 12; n++) { t *= -x * x / ((2 * n) * (2 * n + 1)); s += t; } return s; }
constexpr double cos_s(double x) { double t = 1, s = 1; for (int n = 1; n < 12; n++) { t *= -x * x / ((2 * n - 1) * (2 * n)); s += t; } return s; }
constexpr double cos2048(int m) {
  m &= 2047; if (m > 1024) m = 2048 - m;
  bool neg = false; if (m > 512) { m = 1024 - m; neg = true; }
  double v = (m <= 256) ? cos_s(2 * PI * m / 2048) : sin_s(2 * PI * (512 - m) / 2048);
  return neg ? -v : v;
}
constexpr uint16_t to_bf16(double v) {
  if (v == 0) return 0;
  uint16_t s = 0; if (v < 0) { s = 0x8000; v = -v; }
  int e = 0; while (v >= 2) { v /= 2; e++; } while (v < 1) { v *= 2; e--; }
  double m = (v - 1) * 128; int mi = (int)m; double fr = m - mi;
  if (fr > 0.5 || (fr == 0.5 && (mi & 1))) mi++;
  if (mi == 128) { mi = 0; e++; }
  return (uint16_t)(s | ((e + 127) << 7) | mi);
}
struct CosT { uint16_t v[2048]; constexpr CosT() : v() { for (int i = 0; i < 2048; i++) v[i] = to_bf16(cos2048(i)); } };
struct alignas(1024) FT {
  uint16_t v[512 * 512];
  constexpr FT() : v() {
    CosT c;
    for (int r = 0; r < 512; r++) {
      int k = (r >> 4) * 8 + (r & 7), e = (r >> 3) & 1;
      int mul = 4 * k, add = e ? 512 : 0;
      if (k == 0 && e == 1) { mul = 1024; add = 0; }
      for (int d = 0; d < 512; d++) v[r * 512 + d] = c.v[(d * mul + add) & 2047];
    }
  }
};
struct alignas(1024) ET {
  uint16_t v[2048 * 128];
  constexpr ET() : v() {
    CosT c;
    for (int s = 0; s < 2048; s++)
      for (int j = 0; j < 64; j++) {
        const int o = (s & 31) * 8192 + (s >> 5) * 64 + j;
        v[o] = c.v[(s * j) & 2047]; v[o + 4096] = c.v[(s * j + 512) & 2047];
      }
  }
};
struct alignas(1024) DT {
  uint16_t v[64 * 64];
  constexpr DT() : v() {
    CosT c;
    for (int r = 0; r < 64; r++)
      for (int n = 0; n < 64; n++) {
        const int sg = r >> 1, s0 = (sg & ~6) | ((sg & 2) << 1) | ((sg & 4) >> 1), e = r & 1, f = n & 1;
        const int m = 64 * s0 * (n >> 1) + (e == f ? 0 : e ? -512 : 512);
        v[r * 64 + (((n >> 3) ^ (r & 7)) << 3) + (n & 7)] = c.v[m & 2047];
      }
  }
};
}

__device__ constexpr tbl::FT g_FT = tbl::FT();
__device__ constexpr tbl::ET g_ET = tbl::ET();
__device__ constexpr tbl::DT g_DT = tbl::DT();

__device__ __align__(1024) uint16_t g_X[129 * 8192];
__device__ __align__(1024) uint16_t g_T[32 * 64 * 512];
__device__ __align__(1024) uint2 g_Ts[32 * 64];
__device__ __align__(1024) uint4 g_part[128 * 3 * 1024];
__device__ __align__(16) float g_gate[16 * 128];
__device__ __align__(16) uint2 g_Wh[2 * 2048];
__device__ unsigned g_epoch[132 * 8];
__device__ unsigned g_cntX[8 * 32], g_cntT[8 * 32], g_cntP[128 * 32], g_cntW[32], g_cntH[32];
#define PROF_EV(i) do {} while (0)
#define PROF_CK(i) do {} while (0)

__device__ __forceinline__ uint32_t smem_u32(const void* p) { return (uint32_t)__cvta_generic_to_shared(p); }
__device__ __forceinline__ void mbar_init(uint32_t bar, uint32_t cnt) { asm volatile("mbarrier.init.shared::cta.b64 [%0], %1;" ::"r"(bar), "r"(cnt)); }
__device__ __forceinline__ void mbar_expect_tx(uint32_t bar, uint32_t bytes) { asm volatile("mbarrier.arrive.expect_tx.shared::cta.b64 _, [%0], %1;" ::"r"(bar), "r"(bytes) : "memory"); }
__device__ __forceinline__ void mbar_arrive(uint32_t bar) { asm volatile("mbarrier.arrive.shared::cta.b64 _, [%0];" ::"r"(bar) : "memory"); }
__device__ __forceinline__ void mbar_arrive_if(bool p, uint32_t bar) {
  asm volatile("{\n.reg .pred p;\nsetp.ne.b32 p, %1, 0;\n@p mbarrier.arrive.shared::cta.b64 _, [%0];\n}" ::"r"(bar), "r"((int)p) : "memory");
}
__device__ __forceinline__ void hint_add_if(bool p, unsigned* a) {
  asm volatile("{\n.reg .pred p;\nsetp.ne.b32 p, %1, 0;\n@p red.relaxed.gpu.global.add.u32 [%0], 1;\n}" ::"l"(a), "r"((int)p) : "memory");
}
__device__ __forceinline__ bool mbar_try(uint32_t bar, uint32_t parity) {
  uint32_t ok;
  asm volatile("{\n.reg .pred p;\nmbarrier.test_wait.parity.shared::cta.b64 p, [%1], %2;\nselp.u32 %0, 1, 0, p;\n}" : "=r"(ok) : "r"(bar), "r"(parity) : "memory");
  return ok;
}
__device__ __forceinline__ void mbar_wait(uint32_t bar, uint32_t parity) {
  asm volatile(
      "{\n.reg .pred p;\n.reg .u32 n;\nmov.u32 n, 0;\n"
      "W_LOOP:\nmbarrier.try_wait.parity.shared::cta.b64 p, [%0], %1;\n@p bra W_DONE;\n"
      "add.u32 n, n, 1;\nsetp.lt.u32 p, n, 0x40000;\n@p bra W_LOOP;\ntrap;\nW_DONE:\n}" ::"r"(bar), "r"(parity) : "memory");
}
__device__ __forceinline__ void bulk_load(uint32_t dst, const void* src, uint32_t bytes, uint32_t bar) {
  asm volatile("cp.async.bulk.shared::cluster.global.mbarrier::complete_tx::bytes [%0], [%1], %2, [%3];" ::"r"(dst), "l"(src), "r"(bytes), "r"(bar) : "memory");
}
__device__ __forceinline__ void cp16(uint32_t dst, const void* src) { asm volatile("cp.async.cg.shared.global [%0], [%1], 16;" ::"r"(dst), "l"(src) : "memory"); }
__device__ __forceinline__ void spin_guard(uint32_t t0) { if ((uint32_t)clock() - t0 > (1u << 30)) __trap(); }
__device__ __forceinline__ float tagf(float v, uint32_t tag) { return __uint_as_float((__float_as_uint(v) & ~1u) | tag); }
__device__ __forceinline__ float untag(float v) { return __uint_as_float(__float_as_uint(v) & ~1u); }
__device__ __forceinline__ void st_x2(float2* p, float a, float b) { asm volatile("st.relaxed.gpu.global.v2.f32 [%0], {%1,%2};" ::"l"(p), "f"(a), "f"(b) : "memory"); }
__device__ __forceinline__ float2 ld_x2(const float2* p) { float2 v; asm volatile("ld.relaxed.gpu.global.v2.f32 {%0,%1}, [%2];" : "=f"(v.x), "=f"(v.y) : "l"(p) : "memory"); return v; }
__device__ __forceinline__ void st_u2(uint2* p, uint32_t a, uint32_t b) { asm volatile("st.relaxed.gpu.global.v2.u32 [%0], {%1,%2};" ::"l"(p), "r"(a), "r"(b) : "memory"); }
__device__ __forceinline__ void prefetch2d(const CUtensorMap* m, int c0, int c1) { asm volatile("cp.async.bulk.prefetch.tensor.2d.L2.global [%0, {%1, %2}];" ::"l"(m), "r"(c0), "r"(c1) : "memory"); }
__device__ __forceinline__ void prefetch1d(const void* p, uint32_t bytes) { asm volatile("cp.async.bulk.prefetch.L2.global [%0], %1;" ::"l"(p), "r"(bytes) : "memory"); }
__device__ __forceinline__ uint32_t ld_x1(const void* p) { uint32_t v; asm volatile("ld.relaxed.gpu.global.u32 %0, [%1];" : "=r"(v) : "l"(p) : "memory"); return v; }
__device__ __forceinline__ uint4 ld_x4(const void* p) { uint4 v; asm volatile("ld.relaxed.gpu.global.v4.u32 {%0,%1,%2,%3}, [%4];" : "=r"(v.x), "=r"(v.y), "=r"(v.z), "=r"(v.w) : "l"(p) : "memory"); return v; }
__device__ __forceinline__ void st_x4(void* p, uint32_t a, uint32_t b, uint32_t c, uint32_t d) { asm volatile("st.relaxed.gpu.global.v4.u32 [%0], {%1,%2,%3,%4};" ::"l"(p), "r"(a), "r"(b), "r"(c), "r"(d) : "memory"); }
__device__ __forceinline__ uint32_t mapa(uint32_t a, uint32_t cta) { uint32_t r; asm volatile("mapa.shared::cluster.u32 %0, %1, %2;" : "=r"(r) : "r"(a), "r"(cta)); return r; }
__device__ __forceinline__ void stsm4t(uint32_t a, uint32_t r0, uint32_t r1, uint32_t r2, uint32_t r3) {
  asm volatile("stmatrix.sync.aligned.m8n8.x4.trans.shared.b16 [%0], {%1,%2,%3,%4};" ::"r"(a), "r"(r0), "r"(r1), "r"(r2), "r"(r3) : "memory");
}
__device__ __forceinline__ void hint_add(unsigned* p) { asm volatile("red.relaxed.gpu.global.add.u32 [%0], 1;" ::"l"(p) : "memory"); }
__device__ __forceinline__ void hint_wait(const unsigned* p, unsigned target) {
  const uint32_t t0 = (uint32_t)clock();
  while ((int)(ld_x1(p) - target) < 0) spin_guard(t0);
}
__device__ __forceinline__ void bulk_done_signal(unsigned* p) {
  asm volatile("cp.async.bulk.commit_group;\ncp.async.bulk.wait_group 0;\nfence.proxy.async.global;" ::: "memory");
  hint_add(p);
}
__device__ __forceinline__ void flag_wait(const unsigned* p, unsigned target) {
  hint_wait(p, target);
  asm volatile("fence.proxy.async.global;" ::: "memory");
}
__device__ __forceinline__ void tma2d(uint32_t dst, const CUtensorMap* m, uint32_t bar, int c0, int c1) {
  asm volatile("cp.async.bulk.tensor.2d.shared::cluster.global.mbarrier::complete_tx::bytes [%0], [%1, {%3, %4}], [%2];" ::"r"(dst), "l"(m), "r"(bar), "r"(c0), "r"(c1) : "memory");
}
__device__ __forceinline__ void tma3d(uint32_t dst, const CUtensorMap* m, uint32_t bar, int c0, int c1, int c2) {
  asm volatile("cp.async.bulk.tensor.3d.shared::cluster.global.mbarrier::complete_tx::bytes [%0], [%1, {%3, %4, %5}], [%2];" ::"r"(dst), "l"(m), "r"(bar), "r"(c0), "r"(c1), "r"(c2) : "memory");
}
__device__ __forceinline__ void tma4d(uint32_t dst, const CUtensorMap* m, uint32_t bar, int c0, int c1, int c2, int c3) {
  asm volatile("cp.async.bulk.tensor.4d.shared::cluster.global.mbarrier::complete_tx::bytes [%0], [%1, {%3, %4, %5, %6}], [%2];" ::"r"(dst), "l"(m), "r"(bar), "r"(c0), "r"(c1), "r"(c2), "r"(c3) : "memory");
}
__device__ __forceinline__ void wg_fence() { asm volatile("wgmma.fence.sync.aligned;" ::: "memory"); }
__device__ __forceinline__ void wg_commit() { asm volatile("wgmma.commit_group.sync.aligned;" ::: "memory"); }
template <int N> __device__ __forceinline__ void wg_wait() { asm volatile("wgmma.wait_group.sync.aligned %0;" ::"n"(N) : "memory"); }
template <int O, int N, int NN> __device__ __forceinline__ void fence_regs(float (&d)[NN]) {
#pragma unroll
  for (int i = 0; i < N; i++) asm volatile("" : "+f"(d[O + i])::"memory");
}
__device__ __forceinline__ uint32_t pack_bf16(float lo, float hi) {
  uint32_t r; asm("cvt.rn.bf16x2.f32 %0, %1, %2;" : "=r"(r) : "f"(hi), "f"(lo)); return r;
}
__device__ __forceinline__ uint32_t pack_pin(float lo, float hi) {
  uint32_t r; asm volatile("cvt.rn.bf16x2.f32 %0, %1, %2;" : "=r"(r) : "f"(hi), "f"(lo) : "memory"); return r;
}
__device__ __forceinline__ float bf_lo(uint32_t u) { return __uint_as_float(u << 16); }
__device__ __forceinline__ float bf_hi(uint32_t u) { return __uint_as_float(u & 0xffff0000u); }

__device__ __forceinline__ uint64_t d128(uint32_t lo) { uint64_t d; asm("mov.b64 %0, {%1, 0x40000040};" : "=l"(d) : "r"(lo)); return d; }
__device__ __forceinline__ uint64_t d64(uint32_t lo) { uint64_t d; asm("mov.b64 %0, {%1, 0x80000020};" : "=l"(d) : "r"(lo)); return d; }
template<int O,int TB,int ACC,int NN> __device__ __forceinline__ void mma_ss64(float (&d)[NN], uint64_t da, uint64_t db, int sd = 0){
  if constexpr (ACC == 1) asm volatile("wgmma.mma_async.sync.aligned.m64n64k16.f32.bf16.bf16 {%0,%1,%2,%3,%4,%5,%6,%7,%8,%9,%10,%11,%12,%13,%14,%15,%16,%17,%18,%19,%20,%21,%22,%23,%24,%25,%26,%27,%28,%29,%30,%31}, %32, %33, 1, 1, 1, %35, %34;"
   : "+f"(d[O+0]), "+f"(d[O+1]), "+f"(d[O+2]), "+f"(d[O+3]), "+f"(d[O+4]), "+f"(d[O+5]), "+f"(d[O+6]), "+f"(d[O+7]), "+f"(d[O+8]), "+f"(d[O+9]), "+f"(d[O+10]), "+f"(d[O+11]), "+f"(d[O+12]), "+f"(d[O+13]), "+f"(d[O+14]), "+f"(d[O+15]), "+f"(d[O+16]), "+f"(d[O+17]), "+f"(d[O+18]), "+f"(d[O+19]), "+f"(d[O+20]), "+f"(d[O+21]), "+f"(d[O+22]), "+f"(d[O+23]), "+f"(d[O+24]), "+f"(d[O+25]), "+f"(d[O+26]), "+f"(d[O+27]), "+f"(d[O+28]), "+f"(d[O+29]), "+f"(d[O+30]), "+f"(d[O+31])
   : "l"(da), "l"(db), "n"(TB & 1), "n"(TB >> 1));
  else if constexpr (ACC == 0) asm volatile("wgmma.mma_async.sync.aligned.m64n64k16.f32.bf16.bf16 {%0,%1,%2,%3,%4,%5,%6,%7,%8,%9,%10,%11,%12,%13,%14,%15,%16,%17,%18,%19,%20,%21,%22,%23,%24,%25,%26,%27,%28,%29,%30,%31}, %32, %33, 0, 1, 1, %35, %34;"
   : "=f"(d[O+0]), "=f"(d[O+1]), "=f"(d[O+2]), "=f"(d[O+3]), "=f"(d[O+4]), "=f"(d[O+5]), "=f"(d[O+6]), "=f"(d[O+7]), "=f"(d[O+8]), "=f"(d[O+9]), "=f"(d[O+10]), "=f"(d[O+11]), "=f"(d[O+12]), "=f"(d[O+13]), "=f"(d[O+14]), "=f"(d[O+15]), "=f"(d[O+16]), "=f"(d[O+17]), "=f"(d[O+18]), "=f"(d[O+19]), "=f"(d[O+20]), "=f"(d[O+21]), "=f"(d[O+22]), "=f"(d[O+23]), "=f"(d[O+24]), "=f"(d[O+25]), "=f"(d[O+26]), "=f"(d[O+27]), "=f"(d[O+28]), "=f"(d[O+29]), "=f"(d[O+30]), "=f"(d[O+31])
   : "l"(da), "l"(db), "n"(TB & 1), "n"(TB >> 1));
  else asm volatile("{\n.reg .pred p;\nsetp.ne.b32 p, %36, 0;\nwgmma.mma_async.sync.aligned.m64n64k16.f32.bf16.bf16 {%0,%1,%2,%3,%4,%5,%6,%7,%8,%9,%10,%11,%12,%13,%14,%15,%16,%17,%18,%19,%20,%21,%22,%23,%24,%25,%26,%27,%28,%29,%30,%31}, %32, %33, p, 1, 1, %35, %34;\n}"
   : "+f"(d[O+0]), "+f"(d[O+1]), "+f"(d[O+2]), "+f"(d[O+3]), "+f"(d[O+4]), "+f"(d[O+5]), "+f"(d[O+6]), "+f"(d[O+7]), "+f"(d[O+8]), "+f"(d[O+9]), "+f"(d[O+10]), "+f"(d[O+11]), "+f"(d[O+12]), "+f"(d[O+13]), "+f"(d[O+14]), "+f"(d[O+15]), "+f"(d[O+16]), "+f"(d[O+17]), "+f"(d[O+18]), "+f"(d[O+19]), "+f"(d[O+20]), "+f"(d[O+21]), "+f"(d[O+22]), "+f"(d[O+23]), "+f"(d[O+24]), "+f"(d[O+25]), "+f"(d[O+26]), "+f"(d[O+27]), "+f"(d[O+28]), "+f"(d[O+29]), "+f"(d[O+30]), "+f"(d[O+31])
   : "l"(da), "l"(db), "n"(TB & 1), "n"(TB >> 1), "r"(sd));
}
template<int O,int TB,int ACC,int NN> __device__ __forceinline__ void mma_rs64(float (&d)[NN], uint32_t a0, uint32_t a1, uint32_t a2, uint32_t a3, uint64_t db, int sd = 0){
  if constexpr (ACC == 1) asm volatile("wgmma.mma_async.sync.aligned.m64n64k16.f32.bf16.bf16 {%0,%1,%2,%3,%4,%5,%6,%7,%8,%9,%10,%11,%12,%13,%14,%15,%16,%17,%18,%19,%20,%21,%22,%23,%24,%25,%26,%27,%28,%29,%30,%31}, {%32,%33,%34,%35}, %36, 1, 1, 1, %37;"
   : "+f"(d[O+0]), "+f"(d[O+1]), "+f"(d[O+2]), "+f"(d[O+3]), "+f"(d[O+4]), "+f"(d[O+5]), "+f"(d[O+6]), "+f"(d[O+7]), "+f"(d[O+8]), "+f"(d[O+9]), "+f"(d[O+10]), "+f"(d[O+11]), "+f"(d[O+12]), "+f"(d[O+13]), "+f"(d[O+14]), "+f"(d[O+15]), "+f"(d[O+16]), "+f"(d[O+17]), "+f"(d[O+18]), "+f"(d[O+19]), "+f"(d[O+20]), "+f"(d[O+21]), "+f"(d[O+22]), "+f"(d[O+23]), "+f"(d[O+24]), "+f"(d[O+25]), "+f"(d[O+26]), "+f"(d[O+27]), "+f"(d[O+28]), "+f"(d[O+29]), "+f"(d[O+30]), "+f"(d[O+31])
   : "r"(a0), "r"(a1), "r"(a2), "r"(a3), "l"(db), "n"(TB));
  else if constexpr (ACC == 0) asm volatile("wgmma.mma_async.sync.aligned.m64n64k16.f32.bf16.bf16 {%0,%1,%2,%3,%4,%5,%6,%7,%8,%9,%10,%11,%12,%13,%14,%15,%16,%17,%18,%19,%20,%21,%22,%23,%24,%25,%26,%27,%28,%29,%30,%31}, {%32,%33,%34,%35}, %36, 0, 1, 1, %37;"
   : "=f"(d[O+0]), "=f"(d[O+1]), "=f"(d[O+2]), "=f"(d[O+3]), "=f"(d[O+4]), "=f"(d[O+5]), "=f"(d[O+6]), "=f"(d[O+7]), "=f"(d[O+8]), "=f"(d[O+9]), "=f"(d[O+10]), "=f"(d[O+11]), "=f"(d[O+12]), "=f"(d[O+13]), "=f"(d[O+14]), "=f"(d[O+15]), "=f"(d[O+16]), "=f"(d[O+17]), "=f"(d[O+18]), "=f"(d[O+19]), "=f"(d[O+20]), "=f"(d[O+21]), "=f"(d[O+22]), "=f"(d[O+23]), "=f"(d[O+24]), "=f"(d[O+25]), "=f"(d[O+26]), "=f"(d[O+27]), "=f"(d[O+28]), "=f"(d[O+29]), "=f"(d[O+30]), "=f"(d[O+31])
   : "r"(a0), "r"(a1), "r"(a2), "r"(a3), "l"(db), "n"(TB));
  else asm volatile("{\n.reg .pred p;\nsetp.ne.b32 p, %38, 0;\nwgmma.mma_async.sync.aligned.m64n64k16.f32.bf16.bf16 {%0,%1,%2,%3,%4,%5,%6,%7,%8,%9,%10,%11,%12,%13,%14,%15,%16,%17,%18,%19,%20,%21,%22,%23,%24,%25,%26,%27,%28,%29,%30,%31}, {%32,%33,%34,%35}, %36, p, 1, 1, %37;\n}"
   : "+f"(d[O+0]), "+f"(d[O+1]), "+f"(d[O+2]), "+f"(d[O+3]), "+f"(d[O+4]), "+f"(d[O+5]), "+f"(d[O+6]), "+f"(d[O+7]), "+f"(d[O+8]), "+f"(d[O+9]), "+f"(d[O+10]), "+f"(d[O+11]), "+f"(d[O+12]), "+f"(d[O+13]), "+f"(d[O+14]), "+f"(d[O+15]), "+f"(d[O+16]), "+f"(d[O+17]), "+f"(d[O+18]), "+f"(d[O+19]), "+f"(d[O+20]), "+f"(d[O+21]), "+f"(d[O+22]), "+f"(d[O+23]), "+f"(d[O+24]), "+f"(d[O+25]), "+f"(d[O+26]), "+f"(d[O+27]), "+f"(d[O+28]), "+f"(d[O+29]), "+f"(d[O+30]), "+f"(d[O+31])
   : "r"(a0), "r"(a1), "r"(a2), "r"(a3), "l"(db), "n"(TB), "r"(sd));
}
template<int O,int TB,int ACC,int NN> __device__ __forceinline__ void mma_ss128(float (&d)[NN], uint64_t da, uint64_t db, int sd = 0){
  if constexpr (ACC == 1) asm volatile("wgmma.mma_async.sync.aligned.m64n128k16.f32.bf16.bf16 {%0,%1,%2,%3,%4,%5,%6,%7,%8,%9,%10,%11,%12,%13,%14,%15,%16,%17,%18,%19,%20,%21,%22,%23,%24,%25,%26,%27,%28,%29,%30,%31,%32,%33,%34,%35,%36,%37,%38,%39,%40,%41,%42,%43,%44,%45,%46,%47,%48,%49,%50,%51,%52,%53,%54,%55,%56,%57,%58,%59,%60,%61,%62,%63}, %64, %65, 1, 1, 1, %67, %66;"
   : "+f"(d[O+0]), "+f"(d[O+1]), "+f"(d[O+2]), "+f"(d[O+3]), "+f"(d[O+4]), "+f"(d[O+5]), "+f"(d[O+6]), "+f"(d[O+7]), "+f"(d[O+8]), "+f"(d[O+9]), "+f"(d[O+10]), "+f"(d[O+11]), "+f"(d[O+12]), "+f"(d[O+13]), "+f"(d[O+14]), "+f"(d[O+15]), "+f"(d[O+16]), "+f"(d[O+17]), "+f"(d[O+18]), "+f"(d[O+19]), "+f"(d[O+20]), "+f"(d[O+21]), "+f"(d[O+22]), "+f"(d[O+23]), "+f"(d[O+24]), "+f"(d[O+25]), "+f"(d[O+26]), "+f"(d[O+27]), "+f"(d[O+28]), "+f"(d[O+29]), "+f"(d[O+30]), "+f"(d[O+31]), "+f"(d[O+32]), "+f"(d[O+33]), "+f"(d[O+34]), "+f"(d[O+35]), "+f"(d[O+36]), "+f"(d[O+37]), "+f"(d[O+38]), "+f"(d[O+39]), "+f"(d[O+40]), "+f"(d[O+41]), "+f"(d[O+42]), "+f"(d[O+43]), "+f"(d[O+44]), "+f"(d[O+45]), "+f"(d[O+46]), "+f"(d[O+47]), "+f"(d[O+48]), "+f"(d[O+49]), "+f"(d[O+50]), "+f"(d[O+51]), "+f"(d[O+52]), "+f"(d[O+53]), "+f"(d[O+54]), "+f"(d[O+55]), "+f"(d[O+56]), "+f"(d[O+57]), "+f"(d[O+58]), "+f"(d[O+59]), "+f"(d[O+60]), "+f"(d[O+61]), "+f"(d[O+62]), "+f"(d[O+63])
   : "l"(da), "l"(db), "n"(TB & 1), "n"(TB >> 1));
  else if constexpr (ACC == 0) asm volatile("wgmma.mma_async.sync.aligned.m64n128k16.f32.bf16.bf16 {%0,%1,%2,%3,%4,%5,%6,%7,%8,%9,%10,%11,%12,%13,%14,%15,%16,%17,%18,%19,%20,%21,%22,%23,%24,%25,%26,%27,%28,%29,%30,%31,%32,%33,%34,%35,%36,%37,%38,%39,%40,%41,%42,%43,%44,%45,%46,%47,%48,%49,%50,%51,%52,%53,%54,%55,%56,%57,%58,%59,%60,%61,%62,%63}, %64, %65, 0, 1, 1, %67, %66;"
   : "=f"(d[O+0]), "=f"(d[O+1]), "=f"(d[O+2]), "=f"(d[O+3]), "=f"(d[O+4]), "=f"(d[O+5]), "=f"(d[O+6]), "=f"(d[O+7]), "=f"(d[O+8]), "=f"(d[O+9]), "=f"(d[O+10]), "=f"(d[O+11]), "=f"(d[O+12]), "=f"(d[O+13]), "=f"(d[O+14]), "=f"(d[O+15]), "=f"(d[O+16]), "=f"(d[O+17]), "=f"(d[O+18]), "=f"(d[O+19]), "=f"(d[O+20]), "=f"(d[O+21]), "=f"(d[O+22]), "=f"(d[O+23]), "=f"(d[O+24]), "=f"(d[O+25]), "=f"(d[O+26]), "=f"(d[O+27]), "=f"(d[O+28]), "=f"(d[O+29]), "=f"(d[O+30]), "=f"(d[O+31]), "=f"(d[O+32]), "=f"(d[O+33]), "=f"(d[O+34]), "=f"(d[O+35]), "=f"(d[O+36]), "=f"(d[O+37]), "=f"(d[O+38]), "=f"(d[O+39]), "=f"(d[O+40]), "=f"(d[O+41]), "=f"(d[O+42]), "=f"(d[O+43]), "=f"(d[O+44]), "=f"(d[O+45]), "=f"(d[O+46]), "=f"(d[O+47]), "=f"(d[O+48]), "=f"(d[O+49]), "=f"(d[O+50]), "=f"(d[O+51]), "=f"(d[O+52]), "=f"(d[O+53]), "=f"(d[O+54]), "=f"(d[O+55]), "=f"(d[O+56]), "=f"(d[O+57]), "=f"(d[O+58]), "=f"(d[O+59]), "=f"(d[O+60]), "=f"(d[O+61]), "=f"(d[O+62]), "=f"(d[O+63])
   : "l"(da), "l"(db), "n"(TB & 1), "n"(TB >> 1));
  else asm volatile("{\n.reg .pred p;\nsetp.ne.b32 p, %68, 0;\nwgmma.mma_async.sync.aligned.m64n128k16.f32.bf16.bf16 {%0,%1,%2,%3,%4,%5,%6,%7,%8,%9,%10,%11,%12,%13,%14,%15,%16,%17,%18,%19,%20,%21,%22,%23,%24,%25,%26,%27,%28,%29,%30,%31,%32,%33,%34,%35,%36,%37,%38,%39,%40,%41,%42,%43,%44,%45,%46,%47,%48,%49,%50,%51,%52,%53,%54,%55,%56,%57,%58,%59,%60,%61,%62,%63}, %64, %65, p, 1, 1, %67, %66;\n}"
   : "+f"(d[O+0]), "+f"(d[O+1]), "+f"(d[O+2]), "+f"(d[O+3]), "+f"(d[O+4]), "+f"(d[O+5]), "+f"(d[O+6]), "+f"(d[O+7]), "+f"(d[O+8]), "+f"(d[O+9]), "+f"(d[O+10]), "+f"(d[O+11]), "+f"(d[O+12]), "+f"(d[O+13]), "+f"(d[O+14]), "+f"(d[O+15]), "+f"(d[O+16]), "+f"(d[O+17]), "+f"(d[O+18]), "+f"(d[O+19]), "+f"(d[O+20]), "+f"(d[O+21]), "+f"(d[O+22]), "+f"(d[O+23]), "+f"(d[O+24]), "+f"(d[O+25]), "+f"(d[O+26]), "+f"(d[O+27]), "+f"(d[O+28]), "+f"(d[O+29]), "+f"(d[O+30]), "+f"(d[O+31]), "+f"(d[O+32]), "+f"(d[O+33]), "+f"(d[O+34]), "+f"(d[O+35]), "+f"(d[O+36]), "+f"(d[O+37]), "+f"(d[O+38]), "+f"(d[O+39]), "+f"(d[O+40]), "+f"(d[O+41]), "+f"(d[O+42]), "+f"(d[O+43]), "+f"(d[O+44]), "+f"(d[O+45]), "+f"(d[O+46]), "+f"(d[O+47]), "+f"(d[O+48]), "+f"(d[O+49]), "+f"(d[O+50]), "+f"(d[O+51]), "+f"(d[O+52]), "+f"(d[O+53]), "+f"(d[O+54]), "+f"(d[O+55]), "+f"(d[O+56]), "+f"(d[O+57]), "+f"(d[O+58]), "+f"(d[O+59]), "+f"(d[O+60]), "+f"(d[O+61]), "+f"(d[O+62]), "+f"(d[O+63])
   : "l"(da), "l"(db), "n"(TB & 1), "n"(TB >> 1), "r"(sd));
}
template<int O,int TB,int ACC,int NN> __device__ __forceinline__ void mma_rs128(float (&d)[NN], uint32_t a0, uint32_t a1, uint32_t a2, uint32_t a3, uint64_t db, int sd = 0){
  if constexpr (ACC == 1) asm volatile("wgmma.mma_async.sync.aligned.m64n128k16.f32.bf16.bf16 {%0,%1,%2,%3,%4,%5,%6,%7,%8,%9,%10,%11,%12,%13,%14,%15,%16,%17,%18,%19,%20,%21,%22,%23,%24,%25,%26,%27,%28,%29,%30,%31,%32,%33,%34,%35,%36,%37,%38,%39,%40,%41,%42,%43,%44,%45,%46,%47,%48,%49,%50,%51,%52,%53,%54,%55,%56,%57,%58,%59,%60,%61,%62,%63}, {%64,%65,%66,%67}, %68, 1, 1, 1, %69;"
   : "+f"(d[O+0]), "+f"(d[O+1]), "+f"(d[O+2]), "+f"(d[O+3]), "+f"(d[O+4]), "+f"(d[O+5]), "+f"(d[O+6]), "+f"(d[O+7]), "+f"(d[O+8]), "+f"(d[O+9]), "+f"(d[O+10]), "+f"(d[O+11]), "+f"(d[O+12]), "+f"(d[O+13]), "+f"(d[O+14]), "+f"(d[O+15]), "+f"(d[O+16]), "+f"(d[O+17]), "+f"(d[O+18]), "+f"(d[O+19]), "+f"(d[O+20]), "+f"(d[O+21]), "+f"(d[O+22]), "+f"(d[O+23]), "+f"(d[O+24]), "+f"(d[O+25]), "+f"(d[O+26]), "+f"(d[O+27]), "+f"(d[O+28]), "+f"(d[O+29]), "+f"(d[O+30]), "+f"(d[O+31]), "+f"(d[O+32]), "+f"(d[O+33]), "+f"(d[O+34]), "+f"(d[O+35]), "+f"(d[O+36]), "+f"(d[O+37]), "+f"(d[O+38]), "+f"(d[O+39]), "+f"(d[O+40]), "+f"(d[O+41]), "+f"(d[O+42]), "+f"(d[O+43]), "+f"(d[O+44]), "+f"(d[O+45]), "+f"(d[O+46]), "+f"(d[O+47]), "+f"(d[O+48]), "+f"(d[O+49]), "+f"(d[O+50]), "+f"(d[O+51]), "+f"(d[O+52]), "+f"(d[O+53]), "+f"(d[O+54]), "+f"(d[O+55]), "+f"(d[O+56]), "+f"(d[O+57]), "+f"(d[O+58]), "+f"(d[O+59]), "+f"(d[O+60]), "+f"(d[O+61]), "+f"(d[O+62]), "+f"(d[O+63])
   : "r"(a0), "r"(a1), "r"(a2), "r"(a3), "l"(db), "n"(TB));
  else if constexpr (ACC == 0) asm volatile("wgmma.mma_async.sync.aligned.m64n128k16.f32.bf16.bf16 {%0,%1,%2,%3,%4,%5,%6,%7,%8,%9,%10,%11,%12,%13,%14,%15,%16,%17,%18,%19,%20,%21,%22,%23,%24,%25,%26,%27,%28,%29,%30,%31,%32,%33,%34,%35,%36,%37,%38,%39,%40,%41,%42,%43,%44,%45,%46,%47,%48,%49,%50,%51,%52,%53,%54,%55,%56,%57,%58,%59,%60,%61,%62,%63}, {%64,%65,%66,%67}, %68, 0, 1, 1, %69;"
   : "=f"(d[O+0]), "=f"(d[O+1]), "=f"(d[O+2]), "=f"(d[O+3]), "=f"(d[O+4]), "=f"(d[O+5]), "=f"(d[O+6]), "=f"(d[O+7]), "=f"(d[O+8]), "=f"(d[O+9]), "=f"(d[O+10]), "=f"(d[O+11]), "=f"(d[O+12]), "=f"(d[O+13]), "=f"(d[O+14]), "=f"(d[O+15]), "=f"(d[O+16]), "=f"(d[O+17]), "=f"(d[O+18]), "=f"(d[O+19]), "=f"(d[O+20]), "=f"(d[O+21]), "=f"(d[O+22]), "=f"(d[O+23]), "=f"(d[O+24]), "=f"(d[O+25]), "=f"(d[O+26]), "=f"(d[O+27]), "=f"(d[O+28]), "=f"(d[O+29]), "=f"(d[O+30]), "=f"(d[O+31]), "=f"(d[O+32]), "=f"(d[O+33]), "=f"(d[O+34]), "=f"(d[O+35]), "=f"(d[O+36]), "=f"(d[O+37]), "=f"(d[O+38]), "=f"(d[O+39]), "=f"(d[O+40]), "=f"(d[O+41]), "=f"(d[O+42]), "=f"(d[O+43]), "=f"(d[O+44]), "=f"(d[O+45]), "=f"(d[O+46]), "=f"(d[O+47]), "=f"(d[O+48]), "=f"(d[O+49]), "=f"(d[O+50]), "=f"(d[O+51]), "=f"(d[O+52]), "=f"(d[O+53]), "=f"(d[O+54]), "=f"(d[O+55]), "=f"(d[O+56]), "=f"(d[O+57]), "=f"(d[O+58]), "=f"(d[O+59]), "=f"(d[O+60]), "=f"(d[O+61]), "=f"(d[O+62]), "=f"(d[O+63])
   : "r"(a0), "r"(a1), "r"(a2), "r"(a3), "l"(db), "n"(TB));
  else asm volatile("{\n.reg .pred p;\nsetp.ne.b32 p, %70, 0;\nwgmma.mma_async.sync.aligned.m64n128k16.f32.bf16.bf16 {%0,%1,%2,%3,%4,%5,%6,%7,%8,%9,%10,%11,%12,%13,%14,%15,%16,%17,%18,%19,%20,%21,%22,%23,%24,%25,%26,%27,%28,%29,%30,%31,%32,%33,%34,%35,%36,%37,%38,%39,%40,%41,%42,%43,%44,%45,%46,%47,%48,%49,%50,%51,%52,%53,%54,%55,%56,%57,%58,%59,%60,%61,%62,%63}, {%64,%65,%66,%67}, %68, p, 1, 1, %69;\n}"
   : "+f"(d[O+0]), "+f"(d[O+1]), "+f"(d[O+2]), "+f"(d[O+3]), "+f"(d[O+4]), "+f"(d[O+5]), "+f"(d[O+6]), "+f"(d[O+7]), "+f"(d[O+8]), "+f"(d[O+9]), "+f"(d[O+10]), "+f"(d[O+11]), "+f"(d[O+12]), "+f"(d[O+13]), "+f"(d[O+14]), "+f"(d[O+15]), "+f"(d[O+16]), "+f"(d[O+17]), "+f"(d[O+18]), "+f"(d[O+19]), "+f"(d[O+20]), "+f"(d[O+21]), "+f"(d[O+22]), "+f"(d[O+23]), "+f"(d[O+24]), "+f"(d[O+25]), "+f"(d[O+26]), "+f"(d[O+27]), "+f"(d[O+28]), "+f"(d[O+29]), "+f"(d[O+30]), "+f"(d[O+31]), "+f"(d[O+32]), "+f"(d[O+33]), "+f"(d[O+34]), "+f"(d[O+35]), "+f"(d[O+36]), "+f"(d[O+37]), "+f"(d[O+38]), "+f"(d[O+39]), "+f"(d[O+40]), "+f"(d[O+41]), "+f"(d[O+42]), "+f"(d[O+43]), "+f"(d[O+44]), "+f"(d[O+45]), "+f"(d[O+46]), "+f"(d[O+47]), "+f"(d[O+48]), "+f"(d[O+49]), "+f"(d[O+50]), "+f"(d[O+51]), "+f"(d[O+52]), "+f"(d[O+53]), "+f"(d[O+54]), "+f"(d[O+55]), "+f"(d[O+56]), "+f"(d[O+57]), "+f"(d[O+58]), "+f"(d[O+59]), "+f"(d[O+60]), "+f"(d[O+61]), "+f"(d[O+62]), "+f"(d[O+63])
   : "r"(a0), "r"(a1), "r"(a2), "r"(a3), "l"(db), "n"(TB), "r"(sd));
}

#define NEARLY 0
#define XAHEAD 3
#define HM 2
#define SPACE 100
#define WAFTER 7
#define WPACE 100
#define GATE_AT 4
#define TPACE 40
#define PFMODE 0
#define MAPMODE 0
template <int V> struct IC { static constexpr int value = V; };
struct Maps { CUtensorMap x, ft, g64, u64, e, wr, wi, xs, ts, t, g32, u32, d224; };

constexpr int NCTA = 130;
constexpr int U = 16384;
constexpr int TB = 36864;
constexpr int NR = 4;
constexpr int OFF_RING = 8 * U, OFF_Z = 9 * U, OFF_XB = 12 * U, OFF_T = 13 * U, OFF_D = OFF_T;
constexpr int OFF_BAR = 14 * U, OFF_SP = OFF_BAR + 512;
constexpr int SMEM_BYTES = OFF_SP + 1024 + 128;
constexpr int B_FX = 0, B_FA = 8, B_FT = 12, B_Z = 16, B_W = 20, B_HX = 21, B_TL = 22, B_HP = 23, B_WR = 26, B_E0 = 30;
constexpr int B_EA = 31, B_ET = 35, B_PZ = 39, B_RDY = 41, B_C1 = 42;
constexpr int B_T = 43, B_XS = 44, NBAR = 46;
__host__ __device__ constexpr int rslot(int n) { return n & 3; }
__host__ __device__ constexpr int rpar(int n) { return (n >> 2) & 1; }

__global__ void __cluster_dims__(2, 1, 1) __launch_bounds__(512, 1)
fused_kernel(const __grid_constant__ Maps maps, const __nv_bfloat16* __restrict__ x, const __nv_bfloat16* __restrict__ w_r,
             const __nv_bfloat16* __restrict__ w_i, const __nv_bfloat16* __restrict__ gate_w, __nv_bfloat16* __restrict__ out) {
  extern __shared__ __align__(1024) uint8_t smem[];
  const uint32_t sb = smem_u32(smem);
  const uint32_t bars = sb + OFF_BAR;
  const int tid = threadIdx.x, lane = tid & 31;
  const int warp = __shfl_sync(0xffffffffu, tid >> 5, 0);
  const bool helper = blockIdx.x >= 128;
  const int cl = (blockIdx.x >> 1) & 63, rank = blockIdx.x & 1;
  const int q4 = cl & 3, rb = cl >> 2;
  const int j = 2 * q4 + rank;
  const int f_full = 448 * q4 + (rank ? 256 : 0);
  const int f_half = 448 * q4 + (rank ? 224 : 192);
  const int kg = 2 * j + (rb >> 3), tn = rb & 7;

  if (tid == 64) { PROF_EV(0); PROF_CK(40); }
  auto x_load = [&](int q) {
    mbar_expect_tx(bars + 8 * (B_FX + q), U);
    tma3d(sb + q * U, &maps.x, bars + 8 * (B_FX + q), 64 * q, 0, 2 * rb);
  };
  if (warp < 8) {
    asm volatile("barrier.cluster.arrive.relaxed.aligned;" ::: "memory");
    asm volatile("setmaxnreg.inc.sync.aligned.u32 192;");
    if (tid == 0) PROF_EV(33);
    if (!helper) {
      const int wg = warp >> 2, w = warp & 3, g = lane >> 2;
      const bool elect = (tid & 127) == 0;
      float cX[32], cA[64], cB[64], ci[64], ct[64];
      const int zero = blockIdx.x >> 16;
      uint32_t h[56], yf[16];
      const uint32_t d0 = (sb & 0x3FFFF) >> 4;
      const uint32_t dK = d0 | (1u << 16), dN = d0 | (512u << 16);
      const uint32_t dX = dK + wg * 512;
      constexpr uint32_t RING = OFF_RING >> 4;
      auto waitA = [&](int n) { mbar_wait(bars + 8 * (B_FA + rslot(n)), rpar(n)); };
      auto freeA = [&](int n) { mbar_arrive_if(elect, bars + 8 * (B_EA + rslot(n))); };
      auto nop = [] {};

      if (tid == 0) PROF_EV(34);
      asm volatile("bar.sync 0, 384;" ::: "memory");
      if (tid == 0) PROF_EV(35);
#pragma unroll 1
      for (int kb = 0; kb < 8; kb++) {
        mbar_wait(bars + 8 * (B_FX + kb), 0);
        if (tid == 0 && kb == 0) PROF_EV(36);
        waitA(kb);
        wg_fence();
        const uint64_t dx = d128(dX + kb * 1024), df = d128(dK + (OFF_XB >> 4) + rslot(kb) * 512), db = d128(dN + RING + rslot(kb) * 1024);
        mma_ss64<0, 0, 2>(cX, df, dx, kb);
        mma_ss64<0, 0, 1>(cX, df + 2, dx + 2);
        wg_commit(); wg_wait<1>();
        mbar_arrive_if(elect && kb, bars + 8 * (B_EA + rslot(kb - 1)));
        mma_ss64<0, 0, 1>(cX, df + 4, dx + 4);
        mma_ss64<0, 0, 1>(cX, df + 6, dx + 6);
        wg_commit();
        mma_ss128<0, 1, 2>(cA, dx, db, kb);
#pragma unroll
        for (int k = 1; k < 4; k++) mma_ss128<0, 1, 1>(cA, dx + k * 2, db + k * 128);
        wg_commit();
        if (kb == 0 && tid == 0) PROF_EV(1);
      }
      wg_wait<1>();
      fence_regs<0, 32>(cX);
#pragma unroll
      for (int e = 0; e < 16; e++) yf[e] = pack_pin(cX[2 * e], cX[2 * e + 1]);
      if (tid == 0) PROF_EV(2);
      float o0 = 1.0f, o1 = 1.0f;
      auto glu = [&](auto scaled, auto& acc, int half, int ho, int i0, int i1) {
#pragma unroll
        for (int i = i0; i < i1; i++) {
          float a = fmaxf(acc[2 * i], 0.f) * acc[half + 2 * i], b = fmaxf(acc[2 * i + 1], 0.f) * acc[half + 1 + 2 * i];
          if (decltype(scaled)::value) { const float o = (i & 1) ? o1 : o0; a *= o; b *= o; }
          h[ho + i] = pack_pin(a, b);
        }
      };
      {
        waitA(8); mbar_wait(bars + 8 * B_E0, 0);
        const uint64_t de = d128(dN + (wg ? RING : OFF_XB >> 4));
        wg_fence();
        mma_rs128<0, 1, 0>(cB, yf[0], yf[1], yf[2], yf[3], de);
#pragma unroll
        for (int k = 1; k < 4; k++) mma_rs128<0, 1, 1>(cB, yf[4 * k], yf[4 * k + 1], yf[4 * k + 2], yf[4 * k + 3], de + k * 128);
        wg_commit();
        wg_wait<1>();
        freeA(7);
        mbar_arrive_if(elect, bars + 8 * B_C1);
        fence_regs<0, 64>(cA);
        glu(IC<0>(), cA, 32, 0, 0, 16);
      }
      bool rel = false;
      auto acquire = [&](int n) {
        rel = elect;
        if (!mbar_try(bars + 8 * (B_FA + rslot(n)), rpar(n))) { wg_wait<0>(); freeA(n - 1); rel = false; waitA(n); }
      };
      auto freeP = [&](int n) { mbar_arrive_if(rel, bars + 8 * (B_EA + rslot(n - 1))); };
      auto ffn_step = [&](auto first, auto split, float (&acc)[64], int n, int kb, auto done, auto work) {
        constexpr int SPLIT = decltype(split)::value;
        acquire(n);
        wg_fence();
        const uint64_t dx = d128(dX + kb * 1024), db = d128(dN + RING + rslot(n) * 1024);
        mma_ss128<0, 1, decltype(first)::value>(acc, dx, db, zero);
#pragma unroll
        for (int k = 1; k < SPLIT; k++) mma_ss128<0, 1, 1>(acc, dx + k * 2, db + k * 128);
        wg_commit();
        work();
        wg_wait<1>();
        freeP(n);
        done();
        if (SPLIT < 4) {
          wg_fence();
#pragma unroll
          for (int k = SPLIT; k < 4; k++) mma_ss128<0, 1, 1>(acc, dx + k * 2, db + k * 128);
          wg_commit();
        }
      };
      {
        const int s0 = 2 * rb + wg, kr = 2 * ((s0 & 1) | ((s0 & 4) >> 1));
        const int m = lane >> 3, r = lane & 7;
        const uint32_t a0 = sb + OFF_XB + wg * 8192 + (((w >> 1) * 8 + (m >> 1)) * 2 + (w & 1)) * 256 + (m & 1) * 128 + ((r ^ (kr + (m & 1))) << 4);
        ffn_step(IC<2>(), IC<4>(), cA, 9, 0, [&] { fence_regs<0, 64>(cB); }, nop);
        asm volatile("bar.sync 5, 256;" ::: "memory");
#pragma unroll
        for (int i = 0; i < 4; i++)
          stsm4t(a0 + i * 1024, pack_bf16(cB[8 * i] - cB[34 + 8 * i], cB[8 * i + 1] - cB[35 + 8 * i]),
                 pack_bf16(cB[32 + 8 * i] + cB[8 * i + 2], cB[33 + 8 * i] + cB[8 * i + 3]),
                 pack_bf16(cB[8 * i + 4] - cB[38 + 8 * i], cB[8 * i + 5] - cB[39 + 8 * i]),
                 pack_bf16(cB[36 + 8 * i] + cB[8 * i + 6], cB[37 + 8 * i] + cB[8 * i + 7]));
        if (j == 0 && w == 0) {
          const uint32_t a1 = r ? sb + OFF_SP + 1024 : sb + OFF_SP + wg * 512 + (m & 1) * 256 + (m >> 1) * 128;
#pragma unroll
          for (int n = 0; n < 8; n++)
            asm volatile("stmatrix.sync.aligned.m8n8.x4.shared.b16 [%0], {%1,%2,%3,%4};" ::"r"(a1 + ((n ^ (kr + (m >> 1))) << 4)),
                         "r"(pack_bf16(cB[4 * n], cB[4 * n + 1])), "r"(pack_bf16(cB[4 * n + 2], cB[4 * n + 3])),
                         "r"(pack_bf16(cB[32 + 4 * n], cB[33 + 4 * n])), "r"(pack_bf16(cB[34 + 4 * n], cB[35 + 4 * n])) : "memory");
        }
        ffn_step(IC<1>(), IC<2>(), cA, 10, 1, nop, [&] {
          asm volatile("fence.proxy.async.shared::cta;" ::: "memory");
          __syncwarp();
          mbar_arrive_if(lane == 0, bars + 8 * (B_XS + wg));
          if (tid == 0) PROF_EV(3);
        });
      }
      const float* gp = g_gate + rb * 128 + wg * 64 + w * 16 + g;
      uint32_t gb0 = 0, gb1 = 0, ep = 0;
#pragma unroll 1
      for (int kb = 2; kb < 8; kb++)
        ffn_step(IC<1>(), IC<1>(), cA, 9 + kb, kb, [&] {
          if (kb == 4) { gb0 = ld_x1(gp); gb1 = ld_x1(gp + 8); ep = ld_x1(&g_epoch[blockIdx.x * 8 + (tid >> 12)]); }
        }, nop);
      asm volatile("" : "+r"(ep), "+r"(gb0), "+r"(gb1)::"memory");
      const uint32_t tag = (ep + 1) & 1;
      {
        const uint32_t t0 = (uint32_t)clock();
        while (__any_sync(0xffffffffu, ((gb0 ^ tag) | (gb1 ^ tag)) & 1)) { gb0 = ld_x1(gp); gb1 = ld_x1(gp + 8); spin_guard(t0); }
      }
      const float g0 = __uint_as_float(gb0 & ~1u), g1 = __uint_as_float(gb1 & ~1u);
      o0 = 1.0f - g0; o1 = 1.0f - g1;
      ffn_step(IC<2>(), IC<1>(), cB, 17, 0, [&] { fence_regs<0, 64>(cA); }, [&] {
#pragma unroll
        for (int e = 0; e < 16; e++) { const float o = (e & 1) ? o1 : o0; h[e] = pack_pin(bf_lo(h[e]) * o, bf_hi(h[e]) * o); }
      });
      if (tid == 0) PROF_EV(4);
      ffn_step(IC<1>(), IC<1>(), cB, 18, 1, nop, [&] { glu(IC<1>(), cA, 32, 16, 0, 8); });
      ffn_step(IC<1>(), IC<1>(), cB, 19, 2, nop, [&] { glu(IC<1>(), cA, 32, 16, 8, 16); });
#pragma unroll 1
      for (int kb = 3; kb < 8; kb++) ffn_step(IC<1>(), IC<1>(), cB, 17 + kb, kb, nop, nop);
      if (tid == 0) PROF_EV(5);
      auto m_step = [&](auto first, int i, auto done, auto work) {
        acquire(25 + i);
        wg_fence();
        const uint64_t dx = d128(dX + i * 2048), dm = d64(dN + RING + rslot(25 + i) * 1024);
        mma_ss64<0, 1, decltype(first)::value>(ct, dx, dm);
        mma_ss64<0, 1, 1>(ct, dx + 2, dm + 64);
        wg_commit();
        work();
        wg_wait<1>();
        freeP(25 + i);
        done();
        wg_fence();
#pragma unroll
        for (int k = 2; k < 8; k++) mma_ss64<0, 1, 1>(ct, dx + ((k >> 2) * 1024 + (k & 3) * 2), dm + k * 64);
        wg_commit();
      };
      auto freeT = [&](int t) { mbar_arrive_if(elect, bars + 8 * (B_ET + t)); };
      m_step(IC<0>(), 0, [&] { fence_regs<0, 64>(cB); }, nop);
      m_step(IC<1>(), 1, [&] { freeT(0); }, [&] { glu(IC<1>(), cB, 32, 32, 0, 5); });
      m_step(IC<1>(), 2, [&] { freeT(1); }, [&] { glu(IC<1>(), cB, 32, 32, 5, 11); });
      m_step(IC<1>(), 3, [&] { freeT(2); }, [&] { glu(IC<1>(), cB, 32, 32, 11, 16); });
      waitA(29 + wg);
      if (tid == 0) PROF_EV(6);
      mbar_wait(bars + 8 * (j == 0 ? B_T : B_TL), 0);
      if (tid == 0) PROF_EV(7);
      wg_fence();
      {
        const uint64_t dt = d128(dN + (OFF_T >> 4) + wg * 512), de = d128(dK + RING + (1 + wg) * 1024);
        mma_ss64<0, 1, 0>(ci, de, dt);
        mma_ss64<32, 1, 0>(ci, de + 512, dt);
#pragma unroll
        for (int k = 1; k < 4; k++) {
          mma_ss64<0, 1, 1>(ci, de + k * 2, dt + k * 128);
          mma_ss64<32, 1, 1>(ci, de + (512 + k * 2), dt + k * 128);
        }
        wg_commit();
        wg_wait<1>();
        freeT(3);
        fence_regs<0, 32>(ct);
        glu(IC<1>(), ct, 16, 48, 0, 8);
      }

      auto head = [&](auto off, int t, auto first) {
        constexpr int O = decltype(off)::value;
        mbar_wait(bars + 8 * (B_FT + (t & 3)), t >> 2);
        const uint64_t db = d128(dN + (t & 3) * (TB >> 4) + rank * 256);
        wg_fence();
        mma_rs64<O, 1, decltype(first)::value>(ct, h[0], h[1], h[2], h[3], db, zero);
#pragma unroll
        for (int k = 1; k < 6; k++) mma_rs64<O, 1, 1>(ct, h[4 * k], h[4 * k + 1], h[4 * k + 2], h[4 * k + 3], db + k * 128);
        wg_commit();
        wg_wait<1>();
      };
      auto rest = [&](auto off, int t) {
        constexpr int O = decltype(off)::value;
        const uint64_t db = d128(dN + (t & 3) * (TB >> 4)), dw = db + rank * 256, dm = db + (rank ? 0 : 1536);
        wg_fence();
#pragma unroll
        for (int k = 6; k < 12; k++) mma_rs64<O, 1, 1>(ct, h[4 * k], h[4 * k + 1], h[4 * k + 2], h[4 * k + 3], dw + k * 128);
#pragma unroll
        for (int k = 0; k < 2; k++) mma_rs64<O, 1, 1>(ct, h[48 + 4 * k], h[49 + 4 * k], h[50 + 4 * k], h[51 + 4 * k], dm + k * 128);
#pragma unroll
        for (int k = 0; k < 4; k++) mma_rs64<O, 1, 1>(ct, yf[4 * k], yf[4 * k + 1], yf[4 * k + 2], yf[4 * k + 3], db + (14 + k) * 128);
        wg_commit();
      };
      const uint32_t peerZ = mapa(sb + OFF_Z + tid * 16, rank ^ 1), peerB = mapa(bars + 8 * B_Z, rank ^ 1);
      auto send = [&](auto off, int t) {
        constexpr int O = decltype(off)::value;
        fence_regs<O, 32>(ct);
        const bool grid = t >= 3 && t < 6;
        const int z = grid ? t - 3 : t == 6 ? 3 : t;
        if (grid) {
          mbar_wait(bars + 8 * (B_Z + z), 0);
#pragma unroll
          for (int i = 0; i < 4; i++) {
            const uint4 p = *(const uint4*)(smem + OFF_Z + z * U + i * 4096 + tid * 16);
            const uint32_t a[4] = {p.x, p.y, p.z, p.w};
#pragma unroll
            for (int e = 0; e < 4; e++) { ct[O + 8 * i + 2 * e] += bf_lo(a[e]); ct[O + 8 * i + 2 * e + 1] += bf_hi(a[e]); }
          }
        }
        uint32_t pk[16];
#pragma unroll
        for (int i = 0; i < 16; i++) pk[i] = pack_bf16(ct[O + 2 * i], ct[O + 2 * i + 1]);
        if (grid) {
          const int owner = rb * 8 + 2 * ((q4 + z + 1) & 3) + rank;
          uint4* dst = g_part + (size_t)(owner * 3 + z) * 1024 + tid;
#pragma unroll
          for (int i = 0; i < 4; i++) st_x4(dst + i * 256, (pk[4 * i] & ~1u) | tag, pk[4 * i + 1], pk[4 * i + 2], pk[4 * i + 3]);
          __syncwarp();
          hint_add_if(lane == 0, &g_cntP[32 * owner + z]);
        } else {
#pragma unroll
          for (int i = 0; i < 4; i++)
            asm volatile("st.async.weak.shared::cluster.mbarrier::complete_tx::bytes.v4.b32 [%0], {%1,%2,%3,%4}, [%5];" ::"r"(peerZ + z * U + i * 4096),
                         "r"(pk[4 * i]), "r"(pk[4 * i + 1]), "r"(pk[4 * i + 2]), "r"(pk[4 * i + 3]), "r"(peerB + 8 * z) : "memory");
        }
      };
      asm volatile("barrier.cluster.wait.aligned;" ::: "memory");
      head(IC<0>(), 0, IC<2>());
      if (elect) asm volatile("mbarrier.arrive.shared::cluster.b64 _, [%0];" ::"r"(mapa(bars + 8 * B_RDY, rank ^ 1)) : "memory");
      fence_regs<0, 64>(ci);
#pragma unroll
      for (int i = 0; i < 16; i++) {
        const float gg = ((i & 1) ? g1 : g0) * (2.0f / (2048.0f * 512.0f));
        if (i & 2) yf[i] = pack_pin((ci[2 * i] - ci[28 + 2 * i]) * gg, (ci[2 * i + 1] - ci[29 + 2 * i]) * gg);
        else yf[i] = pack_pin((ci[2 * i] + ci[36 + 2 * i]) * gg, (ci[2 * i + 1] + ci[37 + 2 * i]) * gg);
      }
      if (tid == 0) PROF_EV(8);
#pragma unroll 1
      for (int t = 0;; t += 2) {
        rest(IC<0>(), t);
        head(IC<32>(), t + 1, IC<2>());
        mbar_arrive_if(elect && t < 6, bars + 8 * (B_ET + t));
        if (t == 0) mbar_wait(bars + 8 * B_RDY, 0);
        send(IC<0>(), t);
        rest(IC<32>(), t + 1);
        if (t == 6) break;
        head(IC<0>(), t + 2, IC<2>());
        mbar_arrive_if(elect, bars + 8 * (B_ET + t + 1));
        send(IC<32>(), t + 1);
      }
      if (tid == 0) PROF_EV(9);
      {
        float sum[32];
        mbar_wait(bars + 8 * (B_Z + 3), 0);
#pragma unroll
        for (int i = 0; i < 4; i++) {
          const uint4 p = *(const uint4*)(smem + OFF_Z + 3 * U + i * 4096 + tid * 16);
          const uint32_t a[4] = {p.x, p.y, p.z, p.w};
#pragma unroll
          for (int e = 0; e < 4; e++) { sum[8 * i + 2 * e] = bf_lo(a[e]); sum[8 * i + 2 * e + 1] = bf_hi(a[e]); }
        }
#pragma unroll 1
        for (int z = 0; z < 3; z++) {
          mbar_wait(bars + 8 * (B_HP + z), 0);
          if (z == 2 && tid == 0) PROF_EV(24);
          uint4 pv[4];
#pragma unroll
          for (int i = 0; i < 4; i++) pv[i] = *(const uint4*)(smem + z * U + i * 4096 + tid * 16);
          const uint32_t t0 = (uint32_t)clock();
          while (__any_sync(0xffffffffu, ((pv[0].x ^ tag) | (pv[1].x ^ tag) | (pv[2].x ^ tag) | (pv[3].x ^ tag)) & 1)) {
#pragma unroll
            for (int i = 0; i < 4; i++) pv[i] = ld_x4(g_part + (size_t)((rb * 8 + j) * 3 + z) * 1024 + tid + i * 256);
            spin_guard(t0);
          }
#pragma unroll
          for (int i = 0; i < 4; i++) {
            const uint32_t a[4] = {pv[i].x & ~1u, pv[i].y, pv[i].z, pv[i].w};
#pragma unroll
            for (int e = 0; e < 4; e++) { sum[8 * i + 2 * e] += bf_lo(a[e]); sum[8 * i + 2 * e + 1] += bf_hi(a[e]); }
          }
        }
        if (tid == 0) PROF_EV(14);
        wg_wait<0>();
        fence_regs<32, 32>(ct);
#pragma unroll
        for (int i = 0; i < 32; i++) sum[i] += ct[32 + i];
        const uint32_t stg = sb + OFF_T + warp * 2048;
        const int mr = (lane & 7) + ((lane >> 3) & 1) * 8, mc = lane >> 4;
#pragma unroll
        for (int i = 0; i < 4; i++) {
          const uint32_t a = stg + mr * 128 + (((2 * i + mc) ^ (mr & 7)) << 4);
          asm volatile("stmatrix.sync.aligned.m8n8.x4.shared.b16 [%0], {%1,%2,%3,%4};" ::"r"(a), "r"(pack_bf16(sum[8 * i], sum[8 * i + 1])),
                       "r"(pack_bf16(sum[8 * i + 2], sum[8 * i + 3])), "r"(pack_bf16(sum[8 * i + 4], sum[8 * i + 5])),
                       "r"(pack_bf16(sum[8 * i + 6], sum[8 * i + 7])) : "memory");
        }
        __syncwarp();
#pragma unroll
        for (int i = 0; i < 4; i++) {
          const int r = 4 * i + (lane >> 3), c = lane & 7;
          const uint4 v = *(const uint4*)(smem + OFF_T + warp * 2048 + r * 128 + ((c ^ (r & 7)) << 4));
          *(uint4*)(out + (size_t)(2 * rb + wg + 32 * (16 * w + r)) * 512 + 64 * j + 8 * c) = v;
        }
      }
      if (tid == 0) { g_epoch[blockIdx.x * 8] = ep + 1; PROF_EV(15); PROF_CK(41); }
    }
  } else if (warp < 12) {
    asm volatile("setmaxnreg.dec.sync.aligned.u32 104;");
    asm volatile("barrier.cluster.arrive.relaxed.aligned;" ::: "memory");
    const int t = tid - 256, w = warp - 8;
    const uint32_t ep = ld_x1(&g_epoch[blockIdx.x * 8]);
    const uint32_t tag = (ep + 1) & 1;
    auto gate_rows = [&] {
      const int r = 16 * j + 4 * w + (lane >> 3);
      const uint4* px = (const uint4*)(x + (size_t)(2 * rb + (r >> 6) + 32 * (r & 63)) * 512) + (lane & 7);
      const uint4* pg = (const uint4*)gate_w + (lane & 7);
      {
        float a = 0.f;
#pragma unroll 1
        for (int i = 0; i < 8; i += 4) {
          uint4 u[4], v[4];
#pragma unroll
          for (int e = 0; e < 4; e++) { u[e] = __ldg(px + (i + e) * 8); v[e] = __ldg(pg + (i + e) * 8); }
#pragma unroll
          for (int e = 0; e < 4; e++) {
            a = fmaf(bf_lo(u[e].x), bf_lo(v[e].x), a); a = fmaf(bf_hi(u[e].x), bf_hi(v[e].x), a);
            a = fmaf(bf_lo(u[e].y), bf_lo(v[e].y), a); a = fmaf(bf_hi(u[e].y), bf_hi(v[e].y), a);
            a = fmaf(bf_lo(u[e].z), bf_lo(v[e].z), a); a = fmaf(bf_hi(u[e].z), bf_hi(v[e].z), a);
            a = fmaf(bf_lo(u[e].w), bf_lo(v[e].w), a); a = fmaf(bf_hi(u[e].w), bf_hi(v[e].w), a);
          }
        }
#pragma unroll
        for (int o = 4; o; o >>= 1) a += __shfl_xor_sync(0xffffffffu, a, o);
        if ((lane & 7) == 0)
          asm volatile("st.relaxed.gpu.global.f32 [%0], %1;" ::"l"(g_gate + rb * 128 + r), "f"(tagf(__fdividef(1.0f, 1.0f + __expf(-a)), tag)) : "memory");
        if (t == 0) PROF_EV(18);
      }
      if (w == 0) {
        const int c = lane >> 4, jj = 16 * blockIdx.x + (lane & 15), jm = (2048 - jj) & 2047;
        const unsigned short* pr = (const unsigned short*)w_r + 256 * c;
        const unsigned short* pi = (const unsigned short*)w_i + 256 * c;
        const float wr = 0.25f * (bf_lo(__ldg(pr + jj * 257)) + bf_lo(__ldg(pr + jm * 257)));
        const float wi = 0.25f * (bf_lo(__ldg(pi + jj * 257)) - bf_lo(__ldg(pi + jm * 257)));
        st_u2(g_Wh + c * 2048 + jj, c ? pack_bf16(-wi, wr) : pack_bf16(wr, wi), tag);
        __syncwarp();
        hint_add_if(lane == 0, &g_cntW[0]);
      }
    };
    {
      const int g = lane >> 2, q = lane & 3;
      uint32_t wf[32];
      if (!helper) {
        asm volatile("bar.sync 4, 256;" ::: "memory");
        mbar_wait(bars + 8 * (B_FX + GATE_AT), 0);
        gate_rows();
        const uint32_t wa = sb + OFF_T + w * (3072 + 4) + q * 48 + g * 2;
        mbar_wait(bars + 8 * B_C1, 0);
        if (t == 0) PROF_EV(32);
        __nanosleep(WPACE * w);
#pragma unroll 1
        for (int ri = 0; ri < 2; ri++) {
          if (lane == 0) {
            mbar_expect_tx(bars + 8 * (B_WR + w), 3072);
            tma4d(sb + OFF_T + w * 3072, ri ? &maps.wi : &maps.wr, bars + 8 * (B_WR + w), 16 * kg, 0, 2 * w, tn);
          }
          mbar_wait(bars + 8 * (B_WR + w), ri);
#pragma unroll
          for (int n2 = 0; n2 < 4; n2++) {
            uint32_t v[8];
#pragma unroll
            for (int i = 0; i < 8; i++)
              asm volatile("ld.shared.u16 %0, [%1];" : "=r"(v[i]) : "r"(wa + (2 * n2 + ((i >> 1) & 1)) * 192 + (i & 1) * (1536 + 2) + (i >> 2) * 16) : "memory");
#pragma unroll
            for (int i = 0; i < 8; i++) {
              uint32_t& d = wf[(i >> 2) * 16 + 4 * n2 + (i & 3)];
              d = __byte_perm(d, v[i], 0x5432);
              asm volatile("" : "+r"(d)::"memory");
            }
          }
          __syncwarp();
        }
        asm volatile("bar.sync 1, 128;" ::: "memory");
        if (t == 0) PROF_EV(11);
      } else {
        asm volatile("bar.sync 4, 256;" ::: "memory");
        hint_wait(&g_cntW[0], (ep + 1) * 128u);
        const uint32_t t0 = (uint32_t)clock();
#pragma unroll 1
        for (;;) {
          uint32_t bad = 0;
#pragma unroll
          for (int i = 0; i < 32; i++) {
            const float2 v = ld_x2((const float2*)g_Wh + (i >> 4) * 2048 + 16 * w + g + 8 * (i & 1) + 64 * q + ((i >> 1) & 7) * 256);
            wf[i] = __float_as_uint(v.x); bad |= __float_as_uint(v.y) ^ tag;
          }
          if (!__any_sync(0xffffffffu, bad & 1)) break;
          spin_guard(t0);
        }
        if (t == 0) PROF_EV(11);
      }
      if (t == 0) { mbar_expect_tx(bars + 8 * B_W, 8192); bulk_load(sb + OFF_D, g_DT.v, 8192, bars + 8 * B_W); }
      mbar_wait(bars + 8 * B_W, 0);
      mbar_wait(bars + 8 * B_HX, 0);
      if (t == 0) PROF_EV(12);
      const uint32_t dd = (sb & 0x3FFFF) >> 4;
      const uint64_t dF = d128((dd + (OFF_D >> 4)) | (512u << 16)), dI = d128((dd + (OFF_D >> 4)) | (1u << 16)), dA = d128((dd + (OFF_XB >> 4)) | (512u << 16));
      float az[32];
      const int zero = blockIdx.x >> 16;
      uint32_t pf[32];
#pragma unroll
      for (int mt = 0; mt < 2; mt++) {
        wg_fence();
        if (mt == 0) mma_ss64<0, 3, 0>(az, dA, dF);
        else mma_ss64<0, 3, 2>(az, dA + 512, dF, zero);
#pragma unroll
        for (int k = 1; k < 4; k++) mma_ss64<0, 3, 1>(az, dA + (mt * 512 + k * 128), dF + k * 128);
        wg_commit();
        wg_wait<0>();
        fence_regs<0, 32>(az);
#pragma unroll
        for (int i = 0; i < 16; i++) {
          const float wr = bf_lo(wf[16 * mt + i]), wi = bf_hi(wf[16 * mt + i]);
          pf[16 * mt + i] = pack_pin(fmaf(az[2 * i], wr, -az[2 * i + 1] * wi), fmaf(az[2 * i], wi, az[2 * i + 1] * wr));
        }
      }
      if (t == 0) PROF_EV(16);
#pragma unroll
      for (int mt = 0; mt < 2; mt++) {
        wg_fence();
        mma_rs64<0, 0, 2>(az, pf[16 * mt], pf[16 * mt + 1], pf[16 * mt + 2], pf[16 * mt + 3], dI, mt ? (int)helper : zero);
#pragma unroll
        for (int k = 1; k < 4; k++) mma_rs64<0, 0, 1>(az, pf[16 * mt + 4 * k], pf[16 * mt + 4 * k + 1], pf[16 * mt + 4 * k + 2], pf[16 * mt + 4 * k + 3], dI + k * 2);
        wg_commit();
        wg_wait<0>();
        fence_regs<0, 32>(az);
        if (!helper) {
          const int m = lane >> 3, r = lane & 7;
          const int sl = 2 * (m >> 1) + ((r >> 1) & 1) + 4 * (r >> 2);
          const uint32_t a0 = sb + OFF_XB + (2 * w + (m & 1)) * 2048 + sl * 64 + (((mt * 2 + (r & 1)) ^ (sl >> 1)) << 4);
#pragma unroll
          for (int i = 0; i < 4; i++)
            stsm4t(a0 + i * 512, pack_bf16(az[8 * i], az[8 * i + 1]), pack_bf16(az[8 * i + 2], az[8 * i + 3]), pack_bf16(az[8 * i + 4], az[8 * i + 5]),
                   pack_bf16(az[8 * i + 6], az[8 * i + 7]));
        }
      }
      if (helper) {
#pragma unroll
        for (int i = 0; i < 16; i++) {
          const int n = i >> 1, s0 = 8 * (n >> 1) + 2 * (n & 1) + (q & 1) + 4 * (q >> 1);
          if ((n & 1) == (int)(blockIdx.x & 1)) st_u2(g_Ts + s0 * 64 + 16 * w + g + 8 * (i & 1), pack_bf16(az[2 * i], az[2 * i + 1]), tag);
        }
        __syncwarp();
        hint_add_if(lane == 0, &g_cntH[0]);
        if (t == 0) { g_epoch[blockIdx.x * 8] = ep + 1; PROF_EV(13); }
      } else {
        asm volatile("fence.proxy.async.shared::cta;" ::: "memory");
        __syncwarp();
        if (lane == 0) {
          if (t == 0) PROF_EV(17);
          if (SPACE) __nanosleep(SPACE * w);
          asm volatile("cp.async.bulk.tensor.3d.global.shared::cta.bulk_group [%0, {%2, %3, %4}], [%1];" ::"l"(&maps.ts), "r"(sb + OFF_XB + w * 4096),
                       "r"(32 * kg), "r"(0), "r"(8 * tn + 2 * w) : "memory");
          bulk_done_signal(&g_cntT[32 * j]);
          if (t == 96) PROF_EV(13);
        }
        __syncwarp();
        if (j == 0) {
          hint_wait(&g_cntH[0], (ep + 1) * 8u);
          const uint32_t t0 = (uint32_t)clock();
          float2 v;
          do { v = ld_x2((const float2*)g_Ts + 2 * rb * 64 + t); spin_guard(t0); } while (__any_sync(0xffffffffu, (__float_as_uint(v.y) ^ tag) & 1));
          mbar_wait(bars + 8 * B_TL, 0);
          const uint32_t u = __float_as_uint(v.x);
          *(uint16_t*)(smem + OFF_T + t * 128 + ((t & 7) << 4)) = (uint16_t)u;
          *(uint16_t*)(smem + OFF_T + t * 128 + (((t & 7) ^ 1) << 4)) = (uint16_t)(u >> 16);
          asm volatile("fence.proxy.async.shared::cta;" ::: "memory");
          __syncwarp();
          mbar_arrive_if(lane == 0, bars + 8 * B_T);
        }
      }
    }
  } else {
    asm volatile("setmaxnreg.dec.sync.aligned.u32 24;");
    if (warp < 14) {
      if (lane == 0) {
#pragma unroll
        for (int i = 0; i < 6; i++) mbar_init(bars + 8 * (2 * i + warp - 12), 1);
        asm volatile("fence.proxy.async.shared::cta;" ::: "memory");
      }
      asm volatile("bar.sync 2, 64;" ::: "memory");
      asm volatile("bar.arrive 0, 384;" ::: "memory");
      asm volatile("bar.arrive 4, 256;" ::: "memory");
      if (lane == 0) {
        if (!helper) {
#pragma unroll 1
          for (int n = 0; n < NR; n++) {
            const uint32_t fb = bars + 8 * (B_FA + n);
            if (warp == 12) { x_load(n); mbar_expect_tx(fb, U + 8192); }
            else tma2d(sb + OFF_XB + n * 8192, &maps.ft, fb, 64 * n, 64 * j);
            tma2d(sb + OFF_RING + n * U + (warp - 12) * 8192, &maps.g64 + (warp - 12), fb, f_full, 64 * n);
          }
        }
      }
    } else {
      if (lane != 0) {
      } else if (warp == 15) {
#pragma unroll
        for (int i = B_FT; i < NBAR; i++) mbar_init(bars + 8 * i, i < B_EA ? 1 : i < B_T ? 2 : 4);
#pragma unroll
        for (int i = 0; i < 4; i++) mbar_expect_tx(bars + 8 * (B_Z + i), U);
        asm volatile("fence.mbarrier_init.release.cluster;" ::: "memory");
        asm volatile("fence.proxy.async.shared::cta;" ::: "memory");
      } else {
#pragma unroll
        for (int i = 1; i < 4; i++) asm volatile("prefetch.tensormap [%0];" ::"l"((const char*)&maps + i * 128) : "memory");
      }
      if (lane == 0) PROF_EV(warp + 14);
      __syncwarp();
      asm volatile("bar.arrive 0, 384;" ::: "memory");
      asm volatile("bar.arrive 4, 256;" ::: "memory");
    }
    __syncwarp();
    asm volatile("barrier.cluster.arrive.relaxed.aligned;" ::: "memory");
    asm volatile("bar.sync 3, 128;" ::: "memory");
    if (lane == 0 && (!helper || warp == 15)) {
      if (warp < 14) {
        const int p = warp - 12;
        if (p == 0) x_load(NR);
#pragma unroll 1
        for (int n = NR; n < 31; n++) {
          const bool table = n == 8 || n >= 29;
          const int q = n < 8 ? n : n - 1;
          const CUtensorMap* m = table ? &maps.e : n >= 25 ? &maps.g32 + p : &maps.g64 + p;
          const int c0 = table ? 0 : n >= 25 ? f_half : f_full + 64 * (q >> 3);
          const int c1 = table ? (2 * rb + ((n & 1) ^ 1)) * 128 + 64 * p : n >= 25 ? 128 * (n - 25) : 64 * (q & 7);
          const uint32_t fb = bars + 8 * (B_FA + (n & 3)), dst = sb + OFF_RING + (n & 3) * U + p * 8192;
          const uint32_t bytes = n < 8 ? U + 8192 : U;
          mbar_wait(bars + 8 * (B_EA + (n & 3)), ((n >> 2) & 1) ^ 1);
          tma2d(dst, m, fb, c0, c1);
          if (p == 0) mbar_expect_tx(fb, bytes);
          if (n < 10) {
            if (n < 8 && p == 1) tma2d(sb + OFF_XB + (n & 3) * 8192, &maps.ft, fb, 64 * n, 64 * j);
            if (n < 7 && p == 0) x_load(n + 1);
            if (n == 9) {
              if (p == 0) mbar_expect_tx(bars + 8 * B_E0, U);
              tma2d(sb + OFF_XB + p * 8192, &maps.e, bars + 8 * B_E0, 0, 2 * rb * 128 + 64 * p);
            }
          }
        }
      } else if (warp == 15) {
        const unsigned ep1 = ld_x1(&g_epoch[blockIdx.x * 8]) + 1;
        flag_wait(&g_cntX[helper ? 0 : 32 * j], ep1 * 16u);
        PROF_EV(22);
        mbar_expect_tx(bars + 8 * B_HX, U);
        bulk_load(sb + OFF_XB, g_X + (size_t)(helper ? 128 : kg * 8 + tn) * 8192, U, bars + 8 * B_HX);
        if (!helper) {
          flag_wait(&g_cntT[32 * j], ep1 * 64u);
          PROF_EV(23);
          mbar_expect_tx(bars + 8 * B_TL, U);
          tma3d(sb + OFF_T, &maps.t, bars + 8 * B_TL, 64 * j, 0, 2 * rb);
#pragma unroll 1
          for (int i = 0; i < 3; i++) {
            mbar_wait(bars + 8 * (B_PZ + (i >> 1)), 0);
            flag_wait(&g_cntP[32 * (rb * 8 + j) + i], ep1 * 8u);
            mbar_expect_tx(bars + 8 * (B_HP + i), U);
            bulk_load(sb + i * U, g_part + (size_t)((rb * 8 + j) * 3 + i) * 1024, U, bars + 8 * (B_HP + i));
          }
        }
      } else {
#pragma unroll 1
        for (int h2 = 0; h2 < 2; h2++) {
          const int s0 = 2 * rb + h2, sg = (s0 & ~6) | ((s0 & 2) << 1) | ((s0 & 4) >> 1);
          mbar_wait(bars + 8 * (B_XS + h2), 0);
#pragma unroll 1
          for (int c = 0; c < 2; c++) {
            asm volatile("cp.async.bulk.tensor.4d.global.shared::cta.bulk_group [%0, {%2, %3, %4, %5}], [%1];" ::"l"(&maps.xs),
                         "r"(sb + OFF_XB + h2 * 8192 + c * 4096), "r"(0), "r"(sg), "r"(0), "r"(16 * j + 8 * c) : "memory");
            if (j == 0)
              asm volatile("cp.async.bulk.global.shared::cta.bulk_group [%0], [%1], 256;" ::"l"(g_X + 128 * 8192 + c * 4096 + sg * 128),
                           "r"(sb + OFF_SP + h2 * 512 + c * 256) : "memory");
            if (SPACE && h2 + c < 2) __nanosleep(SPACE);
          }
        }
        bulk_done_signal(&g_cntX[32 * j]);
        PROF_EV(20);
#pragma unroll 1
        for (int t = 0; t < 8; t++) {
          const int i = t < 3 ? t + 1 : t < 6 ? t - 2 : 0;
          const int col = 64 * (2 * ((q4 + i) & 3) + ((t < 3 || t == 6) ? 1 - rank : rank));
          const uint32_t fb = bars + 8 * (B_FT + (t & 3)), dst = sb + (t & 3) * TB;
          mbar_wait(bars + 8 * (B_ET + (t == 2 ? 3 : t & 3)), t >> 2);
          mbar_expect_tx(fb, TB);
          tma2d(dst, &maps.d224, fb, col, 224 * j);
          if (t < 2) mbar_wait(bars + 8 * (B_ET + t + 1), 0);
          tma2d(dst + 28672, &maps.ft, fb, col, 64 * j);
        }
      }
    }
  }
}

typedef CUresult (*EncodeFn)(CUtensorMap*, CUtensorMapDataType, cuuint32_t, void*, const cuuint64_t*, const cuuint64_t*, const cuuint32_t*,
                             const cuuint32_t*, CUtensorMapInterleave, CUtensorMapSwizzle, CUtensorMapL2promotion, CUtensorMapFloatOOBfill);

static void encode(EncodeFn f, CUtensorMap* m, const void* base, int rank, const cuuint64_t* dims, const cuuint64_t* strides, const cuuint32_t* box,
                   CUtensorMapSwizzle sw) {
  cuuint32_t es[5] = {1, 1, 1, 1, 1};
  f(m, CU_TENSOR_MAP_DATA_TYPE_BFLOAT16, rank, (void*)base, dims, strides, box, es, CU_TENSOR_MAP_INTERLEAVE_NONE, sw,
    CU_TENSOR_MAP_L2_PROMOTION_L2_128B, CU_TENSOR_MAP_FLOAT_OOB_FILL_NONE);
}

extern "C" void kernel_launch(void* const* d_in, const int* in_sizes, int n_in, void* d_out, int out_size) {
  (void)in_sizes; (void)n_in; (void)out_size;
  const __nv_bfloat16* x = (const __nv_bfloat16*)d_in[0];
  const __nv_bfloat16* w_r = (const __nv_bfloat16*)d_in[1];
  const __nv_bfloat16* w_i = (const __nv_bfloat16*)d_in[2];
  const __nv_bfloat16* Wg = (const __nv_bfloat16*)d_in[4];
  const __nv_bfloat16* Wu = (const __nv_bfloat16*)d_in[5];
  const __nv_bfloat16* Wd = (const __nv_bfloat16*)d_in[6];
  const __nv_bfloat16* gw = (const __nv_bfloat16*)d_in[7];

  void* fp = nullptr; cudaDriverEntryPointQueryResult qr;
  cudaGetDriverEntryPoint("cuTensorMapEncodeTiled", &fp, cudaEnableDefault, &qr);
  EncodeFn enc = (EncodeFn)fp;
  void *pFT, *pET, *pX, *pT;
  cudaGetSymbolAddress(&pX, g_X); cudaGetSymbolAddress(&pT, g_T);
  cudaGetSymbolAddress(&pFT, g_FT); cudaGetSymbolAddress(&pET, g_ET);

  Maps mp;
  const CUtensorMapSwizzle S128 = CU_TENSOR_MAP_SWIZZLE_128B, S64 = CU_TENSOR_MAP_SWIZZLE_64B;
  { cuuint64_t d[3] = {512, 64, 32}, s[2] = {32768, 1024}; cuuint32_t b[3] = {64, 64, 2}; encode(enc, &mp.x, x, 3, d, s, b, S128); }
  { cuuint64_t d[2] = {512, 512}, s[1] = {1024}; cuuint32_t b[2] = {64, 64}; encode(enc, &mp.ft, pFT, 2, d, s, b, S128); }
  { cuuint64_t d[4] = {128, 32, 2, 129}, s[3] = {256, 8192, 16384}; cuuint32_t b[4] = {128, 1, 2, 8}; encode(enc, &mp.xs, pX, 4, d, s, b, CU_TENSOR_MAP_SWIZZLE_NONE); }
  { cuuint64_t d[3] = {512, 32, 64}, s[2] = {65536, 1024}; cuuint32_t b[3] = {32, 32, 2}; encode(enc, &mp.ts, pT, 3, d, s, b, S64); }
  { cuuint64_t d[3] = {512, 64, 32}, s[2] = {1024, 65536}; cuuint32_t b[3] = {64, 64, 2}; encode(enc, &mp.t, pT, 3, d, s, b, S128); }
  { cuuint64_t d[2] = {64, 4096}, s[1] = {128}; cuuint32_t b[2] = {64, 64}; encode(enc, &mp.e, pET, 2, d, s, b, S128); }
  { cuuint64_t d[2] = {1792, 512}, s[1] = {3584}; cuuint32_t b[2] = {64, 64}, b2[2] = {32, 128};
    encode(enc, &mp.g64, Wg, 2, d, s, b, S128); encode(enc, &mp.u64, Wu, 2, d, s, b, S128);
    encode(enc, &mp.g32, Wg, 2, d, s, b2, S64); encode(enc, &mp.u32, Wu, 2, d, s, b2, S64); }
  { cuuint64_t d[2] = {512, 1792}, s[1] = {1024}; cuuint32_t b[2] = {64, 224}; encode(enc, &mp.d224, Wd, 2, d, s, b, S128); }
  { cuuint64_t d[4] = {264, 32, 8, 8}, s[3] = {32896, 512, 4112}; cuuint32_t b[4] = {24, 32, 2, 1};
    encode(enc, &mp.wr, w_r, 4, d, s, b, CU_TENSOR_MAP_SWIZZLE_NONE); encode(enc, &mp.wi, w_i, 4, d, s, b, CU_TENSOR_MAP_SWIZZLE_NONE); }

  cudaFuncSetAttribute(fused_kernel, cudaFuncAttributeMaxDynamicSharedMemorySize, SMEM_BYTES);
  fused_kernel<<<NCTA, 512, SMEM_BYTES>>>(mp, x, w_r, w_i, gw, (__nv_bfloat16*)d_out);
}
```

```cpp
#include <cuda_runtime.h>
#include <cuda_bf16.h>
#include <cuda.h>
#include <stdint.h>

namespace tbl {
constexpr double PI = 3.14159265358979323846264338327950288;
constexpr double sin_s(double x) { double t = x, s = x; for (int n = 1; n < 12; n++) { t *= -x * x / ((2 * n) * (2 * n + 1)); s += t; } return s; }
constexpr double cos_s(double x) { double t = 1, s = 1; for (int n = 1; n < 12; n++) { t *= -x * x / ((2 * n - 1) * (2 * n)); s += t; } return s; }
constexpr double cos2048(int m) {
  m &= 2047; if (m > 1024) m = 2048 - m;
  bool neg = false; if (m > 512) { m = 1024 - m; neg = true; }
  double v = (m <= 256) ? cos_s(2 * PI * m / 2048) : sin_s(2 * PI * (512 - m) / 2048);
  return neg ? -v : v;
}
constexpr uint16_t to_bf16(double v) {
  if (v == 0) return 0;
  uint16_t s = 0; if (v < 0) { s = 0x8000; v = -v; }
  int e = 0; while (v >= 2) { v /= 2; e++; } while (v < 1) { v *= 2; e--; }
  double m = (v - 1) * 128; int mi = (int)m; double fr = m - mi;
  if (fr > 0.5 || (fr == 0.5 && (mi & 1))) mi++;
  if (mi == 128) { mi = 0; e++; }
  return (uint16_t)(s | ((e + 127) << 7) | mi);
}
struct CosT { uint16_t v[2048]; constexpr CosT() : v() { for (int i = 0; i < 2048; i++) v[i] = to_bf16(cos2048(i)); } };
struct alignas(1024) FT {
  uint16_t v[512 * 512];
  constexpr FT() : v() {
    CosT c;
    for (int r = 0; r < 512; r++) {
      int k = (r >> 4) * 8 + (r & 7), e = (r >> 3) & 1;
      int mul = 4 * k, add = e ? 512 : 0;
      if (k == 0 && e == 1) { mul = 1024; add = 0; }
      for (int d = 0; d < 512; d++) v[r * 512 + d] = c.v[(d * mul + add) & 2047];
    }
  }
};
struct alignas(1024) ET {
  uint16_t v[2048 * 128];
  constexpr ET() : v() {
    CosT c;
    for (int s = 0; s < 2048; s++)
      for (int j = 0; j < 64; j++) {
        const int o = (s & 31) * 8192 + (s >> 5) * 64 + j;
        v[o] = c.v[(s * j) & 2047]; v[o + 4096] = c.v[(s * j + 512) & 2047];
      }
  }
};
struct alignas(1024) DT {
  uint16_t v[64 * 64];
  constexpr DT() : v() {
    CosT c;
    for (int r = 0; r < 64; r++)
      for (int n = 0; n < 64; n++) {
        const int sg = r >> 1, s0 = (sg & ~6) | ((sg & 2) << 1) | ((sg & 4) >> 1), e = r & 1, f = n & 1;
        const int m = 64 * s0 * (n >> 1) + (e == f ? 0 : e ? -512 : 512);
        v[r * 64 + (((n >> 3) ^ (r & 7)) << 3) + (n & 7)] = c.v[m & 2047];
      }
  }
};
}

__device__ constexpr tbl::FT g_FT = tbl::FT();
__device__ constexpr tbl::ET g_ET = tbl::ET();
__device__ constexpr tbl::DT g_DT = tbl::DT();

__device__ __align__(1024) uint16_t g_X[129 * 8192];
__device__ __align__(1024) uint16_t g_T[32 * 64 * 512];
__device__ __align__(1024) uint2 g_Ts[32 * 64];
__device__ __align__(1024) uint4 g_part[128 * 3 * 1024];
__device__ __align__(16) float g_gate[16 * 128];
__device__ __align__(16) uint2 g_Wh[2 * 2048];
__device__ unsigned g_epoch[132 * 8];
__device__ unsigned g_cntX[8 * 32], g_cntT[8 * 32], g_cntP[128 * 32], g_cntW[32], g_cntH[32];
#define PROF_EV(i) do {} while (0)
#define PROF_CK(i) do {} while (0)

__device__ __forceinline__ uint32_t smem_u32(const void* p) { return (uint32_t)__cvta_generic_to_shared(p); }
__device__ __forceinline__ void mbar_init(uint32_t bar, uint32_t cnt) { asm volatile("mbarrier.init.shared::cta.b64 [%0], %1;" ::"r"(bar), "r"(cnt)); }
__device__ __forceinline__ void mbar_expect_tx(uint32_t bar, uint32_t bytes) { asm volatile("mbarrier.arrive.expect_tx.shared::cta.b64 _, [%0], %1;" ::"r"(bar), "r"(bytes) : "memory"); }
__device__ __forceinline__ void mbar_arrive(uint32_t bar) { asm volatile("mbarrier.arrive.shared::cta.b64 _, [%0];" ::"r"(bar) : "memory"); }
__device__ __forceinline__ void mbar_arrive_if(bool p, uint32_t bar) {
  asm volatile("{\n.reg .pred p;\nsetp.ne.b32 p, %1, 0;\n@p mbarrier.arrive.shared::cta.b64 _, [%0];\n}" ::"r"(bar), "r"((int)p) : "memory");
}
__device__ __forceinline__ void hint_add_if(bool p, unsigned* a) {
  asm volatile("{\n.reg .pred p;\nsetp.ne.b32 p, %1, 0;\n@p red.relaxed.gpu.global.add.u32 [%0], 1;\n}" ::"l"(a), "r"((int)p) : "memory");
}
__device__ __forceinline__ bool mbar_try(uint32_t bar, uint32_t parity) {
  uint32_t ok;
  asm volatile("{\n.reg .pred p;\nmbarrier.test_wait.parity.shared::cta.b64 p, [%1], %2;\nselp.u32 %0, 1, 0, p;\n}" : "=r"(ok) : "r"(bar), "r"(parity) : "memory");
  return ok;
}
__device__ __forceinline__ void mbar_wait(uint32_t bar, uint32_t parity) {
  asm volatile(
      "{\n.reg .pred p;\n.reg .u32 n;\nmov.u32 n, 0;\n"
      "W_LOOP:\nmbarrier.try_wait.parity.shared::cta.b64 p, [%0], %1;\n@p bra W_DONE;\n"
      "add.u32 n, n, 1;\nsetp.lt.u32 p, n, 0x40000;\n@p bra W_LOOP;\ntrap;\nW_DONE:\n}" ::"r"(bar), "r"(parity) : "memory");
}
__device__ __forceinline__ void bulk_load(uint32_t dst, const void* src, uint32_t bytes, uint32_t bar) {
  asm volatile("cp.async.bulk.shared::cluster.global.mbarrier::complete_tx::bytes [%0], [%1], %2, [%3];" ::"r"(dst), "l"(src), "r"(bytes), "r"(bar) : "memory");
}
__device__ __forceinline__ void cp16(uint32_t dst, const void* src) { asm volatile("cp.async.cg.shared.global [%0], [%1], 16;" ::"r"(dst), "l"(src) : "memory"); }
__device__ __forceinline__ void spin_guard(uint32_t t0) { if ((uint32_t)clock() - t0 > (1u << 30)) __trap(); }
__device__ __forceinline__ float tagf(float v, uint32_t tag) { return __uint_as_float((__float_as_uint(v) & ~1u) | tag); }
__device__ __forceinline__ float untag(float v) { return __uint_as_float(__float_as_uint(v) & ~1u); }
__device__ __forceinline__ void st_x2(float2* p, float a, float b) { asm volatile("st.relaxed.gpu.global.v2.f32 [%0], {%1,%2};" ::"l"(p), "f"(a), "f"(b) : "memory"); }
__device__ __forceinline__ float2 ld_x2(const float2* p) { float2 v; asm volatile("ld.relaxed.gpu.global.v2.f32 {%0,%1}, [%2];" : "=f"(v.x), "=f"(v.y) : "l"(p) : "memory"); return v; }
__device__ __forceinline__ void st_u2(uint2* p, uint32_t a, uint32_t b) { asm volatile("st.relaxed.gpu.global.v2.u32 [%0], {%1,%2};" ::"l"(p), "r"(a), "r"(b) : "memory"); }
__device__ __forceinline__ void prefetch2d(const CUtensorMap* m, int c0, int c1) { asm volatile("cp.async.bulk.prefetch.tensor.2d.L2.global [%0, {%1, %2}];" ::"l"(m), "r"(c0), "r"(c1) : "memory"); }
__device__ __forceinline__ void prefetch1d(const void* p, uint32_t bytes) { asm volatile("cp.async.bulk.prefetch.L2.global [%0], %1;" ::"l"(p), "r"(bytes) : "memory"); }
__device__ __forceinline__ uint32_t ld_x1(const void* p) { uint32_t v; asm volatile("ld.relaxed.gpu.global.u32 %0, [%1];" : "=r"(v) : "l"(p) : "memory"); return v; }
__device__ __forceinline__ uint4 ld_x4(const void* p) { uint4 v; asm volatile("ld.relaxed.gpu.global.v4.u32 {%0,%1,%2,%3}, [%4];" : "=r"(v.x), "=r"(v.y), "=r"(v.z), "=r"(v.w) : "l"(p) : "memory"); return v; }
__device__ __forceinline__ void st_x4(void* p, uint32_t a, uint32_t b, uint32_t c, uint32_t d) { asm volatile("st.relaxed.gpu.global.v4.u32 [%0], {%1,%2,%3,%4};" ::"l"(p), "r"(a), "r"(b), "r"(c), "r"(d) : "memory"); }
__device__ __forceinline__ uint32_t mapa(uint32_t a, uint32_t cta) { uint32_t r; asm volatile("mapa.shared::cluster.u32 %0, %1, %2;" : "=r"(r) : "r"(a), "r"(cta)); return r; }
__device__ __forceinline__ void stsm4t(uint32_t a, uint32_t r0, uint32_t r1, uint32_t r2, uint32_t r3) {
  asm volatile("stmatrix.sync.aligned.m8n8.x4.trans.shared.b16 [%0], {%1,%2,%3,%4};" ::"r"(a), "r"(r0), "r"(r1), "r"(r2), "r"(r3) : "memory");
}
__device__ __forceinline__ void hint_add(unsigned* p) { asm volatile("red.relaxed.gpu.global.add.u32 [%0], 1;" ::"l"(p) : "memory"); }
__device__ __forceinline__ void hint_wait(const unsigned* p, unsigned target) {
  const uint32_t t0 = (uint32_t)clock();
  while ((int)(ld_x1(p) - target) < 0) spin_guard(t0);
}
__device__ __forceinline__ void bulk_done_signal(unsigned* p) {
  asm volatile("cp.async.bulk.commit_group;\ncp.async.bulk.wait_group 0;\nfence.proxy.async.global;" ::: "memory");
  hint_add(p);
}
__device__ __forceinline__ void flag_wait(const unsigned* p, unsigned target) {
  hint_wait(p, target);
  asm volatile("fence.proxy.async.global;" ::: "memory");
}
__device__ __forceinline__ void tma2d(uint32_t dst, const CUtensorMap* m, uint32_t bar, int c0, int c1) {
  asm volatile("cp.async.bulk.tensor.2d.shared::cluster.global.mbarrier::complete_tx::bytes [%0], [%1, {%3, %4}], [%2];" ::"r"(dst), "l"(m), "r"(bar), "r"(c0), "r"(c1) : "memory");
}
__device__ __forceinline__ void tma3d(uint32_t dst, const CUtensorMap* m, uint32_t bar, int c0, int c1, int c2) {
  asm volatile("cp.async.bulk.tensor.3d.shared::cluster.global.mbarrier::complete_tx::bytes [%0], [%1, {%3, %4, %5}], [%2];" ::"r"(dst), "l"(m), "r"(bar), "r"(c0), "r"(c1), "r"(c2) : "memory");
}
__device__ __forceinline__ void tma4d(uint32_t dst, const CUtensorMap* m, uint32_t bar, int c0, int c1, int c2, int c3) {
  asm volatile("cp.async.bulk.tensor.4d.shared::cluster.global.mbarrier::complete_tx::bytes [%0], [%1, {%3, %4, %5, %6}], [%2];" ::"r"(dst), "l"(m), "r"(bar), "r"(c0), "r"(c1), "r"(c2), "r"(c3) : "memory");
}
__device__ __forceinline__ void wg_fence() { asm volatile("wgmma.fence.sync.aligned;" ::: "memory"); }
__device__ __forceinline__ void wg_commit() { asm volatile("wgmma.commit_group.sync.aligned;" ::: "memory"); }
template <int N> __device__ __forceinline__ void wg_wait() { asm volatile("wgmma.wait_group.sync.aligned %0;" ::"n"(N) : "memory"); }
template <int O, int N, int NN> __device__ __forceinline__ void fence_regs(float (&d)[NN]) {
#pragma unroll
  for (int i = 0; i < N; i++) asm volatile("" : "+f"(d[O + i])::"memory");
}
__device__ __forceinline__ uint32_t pack_bf16(float lo, float hi) {
  uint32_t r; asm("cvt.rn.bf16x2.f32 %0, %1, %2;" : "=r"(r) : "f"(hi), "f"(lo)); return r;
}
__device__ __forceinline__ uint32_t pack_pin(float lo, float hi) {
  uint32_t r; asm volatile("cvt.rn.bf16x2.f32 %0, %1, %2;" : "=r"(r) : "f"(hi), "f"(lo) : "memory"); return r;
}
__device__ __forceinline__ float bf_lo(uint32_t u) { return __uint_as_float(u << 16); }
__device__ __forceinline__ float bf_hi(uint32_t u) { return __uint_as_float(u & 0xffff0000u); }

__device__ __forceinline__ uint64_t d128(uint32_t lo) { uint64_t d; asm("mov.b64 %0, {%1, 0x40000040};" : "=l"(d) : "r"(lo)); return d; }
__device__ __forceinline__ uint64_t d64(uint32_t lo) { uint64_t d; asm("mov.b64 %0, {%1, 0x80000020};" : "=l"(d) : "r"(lo)); return d; }
template<int O,int TB,int ACC,int NN> __device__ __forceinline__ void mma_ss64(float (&d)[NN], uint64_t da, uint64_t db, int sd = 0){
  if constexpr (ACC == 1) asm volatile("wgmma.mma_async.sync.aligned.m64n64k16.f32.bf16.bf16 {%0,%1,%2,%3,%4,%5,%6,%7,%8,%9,%10,%11,%12,%13,%14,%15,%16,%17,%18,%19,%20,%21,%22,%23,%24,%25,%26,%27,%28,%29,%30,%31}, %32, %33, 1, 1, 1, %35, %34;"
   : "+f"(d[O+0]), "+f"(d[O+1]), "+f"(d[O+2]), "+f"(d[O+3]), "+f"(d[O+4]), "+f"(d[O+5]), "+f"(d[O+6]), "+f"(d[O+7]), "+f"(d[O+8]), "+f"(d[O+9]), "+f"(d[O+10]), "+f"(d[O+11]), "+f"(d[O+12]), "+f"(d[O+13]), "+f"(d[O+14]), "+f"(d[O+15]), "+f"(d[O+16]), "+f"(d[O+17]), "+f"(d[O+18]), "+f"(d[O+19]), "+f"(d[O+20]), "+f"(d[O+21]), "+f"(d[O+22]), "+f"(d[O+23]), "+f"(d[O+24]), "+f"(d[O+25]), "+f"(d[O+26]), "+f"(d[O+27]), "+f"(d[O+28]), "+f"(d[O+29]), "+f"(d[O+30]), "+f"(d[O+31])
   : "l"(da), "l"(db), "n"(TB & 1), "n"(TB >> 1));
  else if constexpr (ACC == 0) asm volatile("wgmma.mma_async.sync.aligned.m64n64k16.f32.bf16.bf16 {%0,%1,%2,%3,%4,%5,%6,%7,%8,%9,%10,%11,%12,%13,%14,%15,%16,%17,%18,%19,%20,%21,%22,%23,%24,%25,%26,%27,%28,%29,%30,%31}, %32, %33, 0, 1, 1, %35, %34;"
   : "=f"(d[O+0]), "=f"(d[O+1]), "=f"(d[O+2]), "=f"(d[O+3]), "=f"(d[O+4]), "=f"(d[O+5]), "=f"(d[O+6]), "=f"(d[O+7]), "=f"(d[O+8]), "=f"(d[O+9]), "=f"(d[O+10]), "=f"(d[O+11]), "=f"(d[O+12]), "=f"(d[O+13]), "=f"(d[O+14]), "=f"(d[O+15]), "=f"(d[O+16]), "=f"(d[O+17]), "=f"(d[O+18]), "=f"(d[O+19]), "=f"(d[O+20]), "=f"(d[O+21]), "=f"(d[O+22]), "=f"(d[O+23]), "=f"(d[O+24]), "=f"(d[O+25]), "=f"(d[O+26]), "=f"(d[O+27]), "=f"(d[O+28]), "=f"(d[O+29]), "=f"(d[O+30]), "=f"(d[O+31])
   : "l"(da), "l"(db), "n"(TB & 1), "n"(TB >> 1));
  else asm volatile("{\n.reg .pred p;\nsetp.ne.b32 p, %36, 0;\nwgmma.mma_async.sync.aligned.m64n64k16.f32.bf16.bf16 {%0,%1,%2,%3,%4,%5,%6,%7,%8,%9,%10,%11,%12,%13,%14,%15,%16,%17,%18,%19,%20,%21,%22,%23,%24,%25,%26,%27,%28,%29,%30,%31}, %32, %33, p, 1, 1, %35, %34;\n}"
   : "+f"(d[O+0]), "+f"(d[O+1]), "+f"(d[O+2]), "+f"(d[O+3]), "+f"(d[O+4]), "+f"(d[O+5]), "+f"(d[O+6]), "+f"(d[O+7]), "+f"(d[O+8]), "+f"(d[O+9]), "+f"(d[O+10]), "+f"(d[O+11]), "+f"(d[O+12]), "+f"(d[O+13]), "+f"(d[O+14]), "+f"(d[O+15]), "+f"(d[O+16]), "+f"(d[O+17]), "+f"(d[O+18]), "+f"(d[O+19]), "+f"(d[O+20]), "+f"(d[O+21]), "+f"(d[O+22]), "+f"(d[O+23]), "+f"(d[O+24]), "+f"(d[O+25]), "+f"(d[O+26]), "+f"(d[O+27]), "+f"(d[O+28]), "+f"(d[O+29]), "+f"(d[O+30]), "+f"(d[O+31])
   : "l"(da), "l"(db), "n"(TB & 1), "n"(TB >> 1), "r"(sd));
}
template<int O,int TB,int ACC,int NN> __device__ __forceinline__ void mma_rs64(float (&d)[NN], uint32_t a0, uint32_t a1, uint32_t a2, uint32_t a3, uint64_t db, int sd = 0){
  if constexpr (ACC == 1) asm volatile("wgmma.mma_async.sync.aligned.m64n64k16.f32.bf16.bf16 {%0,%1,%2,%3,%4,%5,%6,%7,%8,%9,%10,%11,%12,%13,%14,%15,%16,%17,%18,%19,%20,%21,%22,%23,%24,%25,%26,%27,%28,%29,%30,%31}, {%32,%33,%34,%35}, %36, 1, 1, 1, %37;"
   : "+f"(d[O+0]), "+f"(d[O+1]), "+f"(d[O+2]), "+f"(d[O+3]), "+f"(d[O+4]), "+f"(d[O+5]), "+f"(d[O+6]), "+f"(d[O+7]), "+f"(d[O+8]), "+f"(d[O+9]), "+f"(d[O+10]), "+f"(d[O+11]), "+f"(d[O+12]), "+f"(d[O+13]), "+f"(d[O+14]), "+f"(d[O+15]), "+f"(d[O+16]), "+f"(d[O+17]), "+f"(d[O+18]), "+f"(d[O+19]), "+f"(d[O+20]), "+f"(d[O+21]), "+f"(d[O+22]), "+f"(d[O+23]), "+f"(d[O+24]), "+f"(d[O+25]), "+f"(d[O+26]), "+f"(d[O+27]), "+f"(d[O+28]), "+f"(d[O+29]), "+f"(d[O+30]), "+f"(d[O+31])
   : "r"(a0), "r"(a1), "r"(a2), "r"(a3), "l"(db), "n"(TB));
  else if constexpr (ACC == 0) asm volatile("wgmma.mma_async.sync.aligned.m64n64k16.f32.bf16.bf16 {%0,%1,%2,%3,%4,%5,%6,%7,%8,%9,%10,%11,%12,%13,%14,%15,%16,%17,%18,%19,%20,%21,%22,%23,%24,%25,%26,%27,%28,%29,%30,%31}, {%32,%33,%34,%35}, %36, 0, 1, 1, %37;"
   : "=f"(d[O+0]), "=f"(d[O+1]), "=f"(d[O+2]), "=f"(d[O+3]), "=f"(d[O+4]), "=f"(d[O+5]), "=f"(d[O+6]), "=f"(d[O+7]), "=f"(d[O+8]), "=f"(d[O+9]), "=f"(d[O+10]), "=f"(d[O+11]), "=f"(d[O+12]), "=f"(d[O+13]), "=f"(d[O+14]), "=f"(d[O+15]), "=f"(d[O+16]), "=f"(d[O+17]), "=f"(d[O+18]), "=f"(d[O+19]), "=f"(d[O+20]), "=f"(d[O+21]), "=f"(d[O+22]), "=f"(d[O+23]), "=f"(d[O+24]), "=f"(d[O+25]), "=f"(d[O+26]), "=f"(d[O+27]), "=f"(d[O+28]), "=f"(d[O+29]), "=f"(d[O+30]), "=f"(d[O+31])
   : "r"(a0), "r"(a1), "r"(a2), "r"(a3), "l"(db), "n"(TB));
  else asm volatile("{\n.reg .pred p;\nsetp.ne.b32 p, %38, 0;\nwgmma.mma_async.sync.aligned.m64n64k16.f32.bf16.bf16 {%0,%1,%2,%3,%4,%5,%6,%7,%8,%9,%10,%11,%12,%13,%14,%15,%16,%17,%18,%19,%20,%21,%22,%23,%24,%25,%26,%27,%28,%29,%30,%31}, {%32,%33,%34,%35}, %36, p, 1, 1, %37;\n}"
   : "+f"(d[O+0]), "+f"(d[O+1]), "+f"(d[O+2]), "+f"(d[O+3]), "+f"(d[O+4]), "+f"(d[O+5]), "+f"(d[O+6]), "+f"(d[O+7]), "+f"(d[O+8]), "+f"(d[O+9]), "+f"(d[O+10]), "+f"(d[O+11]), "+f"(d[O+12]), "+f"(d[O+13]), "+f"(d[O+14]), "+f"(d[O+15]), "+f"(d[O+16]), "+f"(d[O+17]), "+f"(d[O+18]), "+f"(d[O+19]), "+f"(d[O+20]), "+f"(d[O+21]), "+f"(d[O+22]), "+f"(d[O+23]), "+f"(d[O+24]), "+f"(d[O+25]), "+f"(d[O+26]), "+f"(d[O+27]), "+f"(d[O+28]), "+f"(d[O+29]), "+f"(d[O+30]), "+f"(d[O+31])
   : "r"(a0), "r"(a1), "r"(a2), "r"(a3), "l"(db), "n"(TB), "r"(sd));
}
template<int O,int TB,int ACC,int NN> __device__ __forceinline__ void mma_ss128(float (&d)[NN], uint64_t da, uint64_t db, int sd = 0){
  if constexpr (ACC == 1) asm volatile("wgmma.mma_async.sync.aligned.m64n128k16.f32.bf16.bf16 {%0,%1,%2,%3,%4,%5,%6,%7,%8,%9,%10,%11,%12,%13,%14,%15,%16,%17,%18,%19,%20,%21,%22,%23,%24,%25,%26,%27,%28,%29,%30,%31,%32,%33,%34,%35,%36,%37,%38,%39,%40,%41,%42,%43,%44,%45,%46,%47,%48,%49,%50,%51,%52,%53,%54,%55,%56,%57,%58,%59,%60,%61,%62,%63}, %64, %65, 1, 1, 1, %67, %66;"
   : "+f"(d[O+0]), "+f"(d[O+1]), "+f"(d[O+2]), "+f"(d[O+3]), "+f"(d[O+4]), "+f"(d[O+5]), "+f"(d[O+6]), "+f"(d[O+7]), "+f"(d[O+8]), "+f"(d[O+9]), "+f"(d[O+10]), "+f"(d[O+11]), "+f"(d[O+12]), "+f"(d[O+13]), "+f"(d[O+14]), "+f"(d[O+15]), "+f"(d[O+16]), "+f"(d[O+17]), "+f"(d[O+18]), "+f"(d[O+19]), "+f"(d[O+20]), "+f"(d[O+21]), "+f"(d[O+22]), "+f"(d[O+23]), "+f"(d[O+24]), "+f"(d[O+25]), "+f"(d[O+26]), "+f"(d[O+27]), "+f"(d[O+28]), "+f"(d[O+29]), "+f"(d[O+30]), "+f"(d[O+31]), "+f"(d[O+32]), "+f"(d[O+33]), "+f"(d[O+34]), "+f"(d[O+35]), "+f"(d[O+36]), "+f"(d[O+37]), "+f"(d[O+38]), "+f"(d[O+39]), "+f"(d[O+40]), "+f"(d[O+41]), "+f"(d[O+42]), "+f"(d[O+43]), "+f"(d[O+44]), "+f"(d[O+45]), "+f"(d[O+46]), "+f"(d[O+47]), "+f"(d[O+48]), "+f"(d[O+49]), "+f"(d[O+50]), "+f"(d[O+51]), "+f"(d[O+52]), "+f"(d[O+53]), "+f"(d[O+54]), "+f"(d[O+55]), "+f"(d[O+56]), "+f"(d[O+57]), "+f"(d[O+58]), "+f"(d[O+59]), "+f"(d[O+60]), "+f"(d[O+61]), "+f"(d[O+62]), "+f"(d[O+63])
   : "l"(da), "l"(db), "n"(TB & 1), "n"(TB >> 1));
  else if constexpr (ACC == 0) asm volatile("wgmma.mma_async.sync.aligned.m64n128k16.f32.bf16.bf16 {%0,%1,%2,%3,%4,%5,%6,%7,%8,%9,%10,%11,%12,%13,%14,%15,%16,%17,%18,%19,%20,%21,%22,%23,%24,%25,%26,%27,%28,%29,%30,%31,%32,%33,%34,%35,%36,%37,%38,%39,%40,%41,%42,%43,%44,%45,%46,%47,%48,%49,%50,%51,%52,%53,%54,%55,%56,%57,%58,%59,%60,%61,%62,%63}, %64, %65, 0, 1, 1, %67, %66;"
   : "=f"(d[O+0]), "=f"(d[O+1]), "=f"(d[O+2]), "=f"(d[O+3]), "=f"(d[O+4]), "=f"(d[O+5]), "=f"(d[O+6]), "=f"(d[O+7]), "=f"(d[O+8]), "=f"(d[O+9]), "=f"(d[O+10]), "=f"(d[O+11]), "=f"(d[O+12]), "=f"(d[O+13]), "=f"(d[O+14]), "=f"(d[O+15]), "=f"(d[O+16]), "=f"(d[O+17]), "=f"(d[O+18]), "=f"(d[O+19]), "=f"(d[O+20]), "=f"(d[O+21]), "=f"(d[O+22]), "=f"(d[O+23]), "=f"(d[O+24]), "=f"(d[O+25]), "=f"(d[O+26]), "=f"(d[O+27]), "=f"(d[O+28]), "=f"(d[O+29]), "=f"(d[O+30]), "=f"(d[O+31]), "=f"(d[O+32]), "=f"(d[O+33]), "=f"(d[O+34]), "=f"(d[O+35]), "=f"(d[O+36]), "=f"(d[O+37]), "=f"(d[O+38]), "=f"(d[O+39]), "=f"(d[O+40]), "=f"(d[O+41]), "=f"(d[O+42]), "=f"(d[O+43]), "=f"(d[O+44]), "=f"(d[O+45]), "=f"(d[O+46]), "=f"(d[O+47]), "=f"(d[O+48]), "=f"(d[O+49]), "=f"(d[O+50]), "=f"(d[O+51]), "=f"(d[O+52]), "=f"(d[O+53]), "=f"(d[O+54]), "=f"(d[O+55]), "=f"(d[O+56]), "=f"(d[O+57]), "=f"(d[O+58]), "=f"(d[O+59]), "=f"(d[O+60]), "=f"(d[O+61]), "=f"(d[O+62]), "=f"(d[O+63])
   : "l"(da), "l"(db), "n"(TB & 1), "n"(TB >> 1));
  else asm volatile("{\n.reg .pred p;\nsetp.ne.b32 p, %68, 0;\nwgmma.mma_async.sync.aligned.m64n128k16.f32.bf16.bf16 {%0,%1,%2,%3,%4,%5,%6,%7,%8,%9,%10,%11,%12,%13,%14,%15,%16,%17,%18,%19,%20,%21,%22,%23,%24,%25,%26,%27,%28,%29,%30,%31,%32,%33,%34,%35,%36,%37,%38,%39,%40,%41,%42,%43,%44,%45,%46,%47,%48,%49,%50,%51,%52,%53,%54,%55,%56,%57,%58,%59,%60,%61,%62,%63}, %64, %65, p, 1, 1, %67, %66;\n}"
   : "+f"(d[O+0]), "+f"(d[O+1]), "+f"(d[O+2]), "+f"(d[O+3]), "+f"(d[O+4]), "+f"(d[O+5]), "+f"(d[O+6]), "+f"(d[O+7]), "+f"(d[O+8]), "+f"(d[O+9]), "+f"(d[O+10]), "+f"(d[O+11]), "+f"(d[O+12]), "+f"(d[O+13]), "+f"(d[O+14]), "+f"(d[O+15]), "+f"(d[O+16]), "+f"(d[O+17]), "+f"(d[O+18]), "+f"(d[O+19]), "+f"(d[O+20]), "+f"(d[O+21]), "+f"(d[O+22]), "+f"(d[O+23]), "+f"(d[O+24]), "+f"(d[O+25]), "+f"(d[O+26]), "+f"(d[O+27]), "+f"(d[O+28]), "+f"(d[O+29]), "+f"(d[O+30]), "+f"(d[O+31]), "+f"(d[O+32]), "+f"(d[O+33]), "+f"(d[O+34]), "+f"(d[O+35]), "+f"(d[O+36]), "+f"(d[O+37]), "+f"(d[O+38]), "+f"(d[O+39]), "+f"(d[O+40]), "+f"(d[O+41]), "+f"(d[O+42]), "+f"(d[O+43]), "+f"(d[O+44]), "+f"(d[O+45]), "+f"(d[O+46]), "+f"(d[O+47]), "+f"(d[O+48]), "+f"(d[O+49]), "+f"(d[O+50]), "+f"(d[O+51]), "+f"(d[O+52]), "+f"(d[O+53]), "+f"(d[O+54]), "+f"(d[O+55]), "+f"(d[O+56]), "+f"(d[O+57]), "+f"(d[O+58]), "+f"(d[O+59]), "+f"(d[O+60]), "+f"(d[O+61]), "+f"(d[O+62]), "+f"(d[O+63])
   : "l"(da), "l"(db), "n"(TB & 1), "n"(TB >> 1), "r"(sd));
}
template<int O,int TB,int ACC,int NN> __device__ __forceinline__ void mma_rs128(float (&d)[NN], uint32_t a0, uint32_t a1, uint32_t a2, uint32_t a3, uint64_t db, int sd = 0){
  if constexpr (ACC == 1) asm volatile("wgmma.mma_async.sync.aligned.m64n128k16.f32.bf16.bf16 {%0,%1,%2,%3,%4,%5,%6,%7,%8,%9,%10,%11,%12,%13,%14,%15,%16,%17,%18,%19,%20,%21,%22,%23,%24,%25,%26,%27,%28,%29,%30,%31,%32,%33,%34,%35,%36,%37,%38,%39,%40,%41,%42,%43,%44,%45,%46,%47,%48,%49,%50,%51,%52,%53,%54,%55,%56,%57,%58,%59,%60,%61,%62,%63}, {%64,%65,%66,%67}, %68, 1, 1, 1, %69;"
   : "+f"(d[O+0]), "+f"(d[O+1]), "+f"(d[O+2]), "+f"(d[O+3]), "+f"(d[O+4]), "+f"(d[O+5]), "+f"(d[O+6]), "+f"(d[O+7]), "+f"(d[O+8]), "+f"(d[O+9]), "+f"(d[O+10]), "+f"(d[O+11]), "+f"(d[O+12]), "+f"(d[O+13]), "+f"(d[O+14]), "+f"(d[O+15]), "+f"(d[O+16]), "+f"(d[O+17]), "+f"(d[O+18]), "+f"(d[O+19]), "+f"(d[O+20]), "+f"(d[O+21]), "+f"(d[O+22]), "+f"(d[O+23]), "+f"(d[O+24]), "+f"(d[O+25]), "+f"(d[O+26]), "+f"(d[O+27]), "+f"(d[O+28]), "+f"(d[O+29]), "+f"(d[O+30]), "+f"(d[O+31]), "+f"(d[O+32]), "+f"(d[O+33]), "+f"(d[O+34]), "+f"(d[O+35]), "+f"(d[O+36]), "+f"(d[O+37]), "+f"(d[O+38]), "+f"(d[O+39]), "+f"(d[O+40]), "+f"(d[O+41]), "+f"(d[O+42]), "+f"(d[O+43]), "+f"(d[O+44]), "+f"(d[O+45]), "+f"(d[O+46]), "+f"(d[O+47]), "+f"(d[O+48]), "+f"(d[O+49]), "+f"(d[O+50]), "+f"(d[O+51]), "+f"(d[O+52]), "+f"(d[O+53]), "+f"(d[O+54]), "+f"(d[O+55]), "+f"(d[O+56]), "+f"(d[O+57]), "+f"(d[O+58]), "+f"(d[O+59]), "+f"(d[O+60]), "+f"(d[O+61]), "+f"(d[O+62]), "+f"(d[O+63])
   : "r"(a0), "r"(a1), "r"(a2), "r"(a3), "l"(db), "n"(TB));
  else if constexpr (ACC == 0) asm volatile("wgmma.mma_async.sync.aligned.m64n128k16.f32.bf16.bf16 {%0,%1,%2,%3,%4,%5,%6,%7,%8,%9,%10,%11,%12,%13,%14,%15,%16,%17,%18,%19,%20,%21,%22,%23,%24,%25,%26,%27,%28,%29,%30,%31,%32,%33,%34,%35,%36,%37,%38,%39,%40,%41,%42,%43,%44,%45,%46,%47,%48,%49,%50,%51,%52,%53,%54,%55,%56,%57,%58,%59,%60,%61,%62,%63}, {%64,%65,%66,%67}, %68, 0, 1, 1, %69;"
   : "=f"(d[O+0]), "=f"(d[O+1]), "=f"(d[O+2]), "=f"(d[O+3]), "=f"(d[O+4]), "=f"(d[O+5]), "=f"(d[O+6]), "=f"(d[O+7]), "=f"(d[O+8]), "=f"(d[O+9]), "=f"(d[O+10]), "=f"(d[O+11]), "=f"(d[O+12]), "=f"(d[O+13]), "=f"(d[O+14]), "=f"(d[O+15]), "=f"(d[O+16]), "=f"(d[O+17]), "=f"(d[O+18]), "=f"(d[O+19]), "=f"(d[O+20]), "=f"(d[O+21]), "=f"(d[O+22]), "=f"(d[O+23]), "=f"(d[O+24]), "=f"(d[O+25]), "=f"(d[O+26]), "=f"(d[O+27]), "=f"(d[O+28]), "=f"(d[O+29]), "=f"(d[O+30]), "=f"(d[O+31]), "=f"(d[O+32]), "=f"(d[O+33]), "=f"(d[O+34]), "=f"(d[O+35]), "=f"(d[O+36]), "=f"(d[O+37]), "=f"(d[O+38]), "=f"(d[O+39]), "=f"(d[O+40]), "=f"(d[O+41]), "=f"(d[O+42]), "=f"(d[O+43]), "=f"(d[O+44]), "=f"(d[O+45]), "=f"(d[O+46]), "=f"(d[O+47]), "=f"(d[O+48]), "=f"(d[O+49]), "=f"(d[O+50]), "=f"(d[O+51]), "=f"(d[O+52]), "=f"(d[O+53]), "=f"(d[O+54]), "=f"(d[O+55]), "=f"(d[O+56]), "=f"(d[O+57]), "=f"(d[O+58]), "=f"(d[O+59]), "=f"(d[O+60]), "=f"(d[O+61]), "=f"(d[O+62]), "=f"(d[O+63])
   : "r"(a0), "r"(a1), "r"(a2), "r"(a3), "l"(db), "n"(TB));
  else asm volatile("{\n.reg .pred p;\nsetp.ne.b32 p, %70, 0;\nwgmma.mma_async.sync.aligned.m64n128k16.f32.bf16.bf16 {%0,%1,%2,%3,%4,%5,%6,%7,%8,%9,%10,%11,%12,%13,%14,%15,%16,%17,%18,%19,%20,%21,%22,%23,%24,%25,%26,%27,%28,%29,%30,%31,%32,%33,%34,%35,%36,%37,%38,%39,%40,%41,%42,%43,%44,%45,%46,%47,%48,%49,%50,%51,%52,%53,%54,%55,%56,%57,%58,%59,%60,%61,%62,%63}, {%64,%65,%66,%67}, %68, p, 1, 1, %69;\n}"
   : "+f"(d[O+0]), "+f"(d[O+1]), "+f"(d[O+2]), "+f"(d[O+3]), "+f"(d[O+4]), "+f"(d[O+5]), "+f"(d[O+6]), "+f"(d[O+7]), "+f"(d[O+8]), "+f"(d[O+9]), "+f"(d[O+10]), "+f"(d[O+11]), "+f"(d[O+12]), "+f"(d[O+13]), "+f"(d[O+14]), "+f"(d[O+15]), "+f"(d[O+16]), "+f"(d[O+17]), "+f"(d[O+18]), "+f"(d[O+19]), "+f"(d[O+20]), "+f"(d[O+21]), "+f"(d[O+22]), "+f"(d[O+23]), "+f"(d[O+24]), "+f"(d[O+25]), "+f"(d[O+26]), "+f"(d[O+27]), "+f"(d[O+28]), "+f"(d[O+29]), "+f"(d[O+30]), "+f"(d[O+31]), "+f"(d[O+32]), "+f"(d[O+33]), "+f"(d[O+34]), "+f"(d[O+35]), "+f"(d[O+36]), "+f"(d[O+37]), "+f"(d[O+38]), "+f"(d[O+39]), "+f"(d[O+40]), "+f"(d[O+41]), "+f"(d[O+42]), "+f"(d[O+43]), "+f"(d[O+44]), "+f"(d[O+45]), "+f"(d[O+46]), "+f"(d[O+47]), "+f"(d[O+48]), "+f"(d[O+49]), "+f"(d[O+50]), "+f"(d[O+51]), "+f"(d[O+52]), "+f"(d[O+53]), "+f"(d[O+54]), "+f"(d[O+55]), "+f"(d[O+56]), "+f"(d[O+57]), "+f"(d[O+58]), "+f"(d[O+59]), "+f"(d[O+60]), "+f"(d[O+61]), "+f"(d[O+62]), "+f"(d[O+63])
   : "r"(a0), "r"(a1), "r"(a2), "r"(a3), "l"(db), "n"(TB), "r"(sd));
}

#define NEARLY 0
#define XAHEAD 3
#define HM 2
#define SPACE 0
#define WPF 0
#define WAFTER 7
#define WPACE 0
#define GATE_AT 4
#define TPACE 40
#define PFMODE 0
#define MAPMODE 0
template <int V> struct IC { static constexpr int value = V; };
struct Maps { CUtensorMap x, ft, g64, u64, e, wr, wi, xs, ts, t, g32, u32, d224; };

constexpr int NCTA = 130;
constexpr int U = 16384;
constexpr int TB = 36864;
constexpr int NR = 4;
constexpr int OFF_RING = 8 * U, OFF_Z = 9 * U, OFF_XB = 12 * U, OFF_T = 13 * U, OFF_D = OFF_T;
constexpr int OFF_BAR = 14 * U, OFF_SP = OFF_BAR + 512, OFF_G = OFF_SP + 1024 + 128;
constexpr int SMEM_BYTES = OFF_G + 512;
constexpr int B_FX = 0, B_FA = 8, B_FT = 12, B_Z = 16, B_W = 20, B_HX = 21, B_TL = 22, B_HP = 23, B_WR = 26, B_E0 = 30;
constexpr int B_EA = 31, B_ET = 35, B_PZ = 39, B_RDY = 41, B_C1 = 42;
constexpr int B_T = 43, B_XS = 44, B_G = 46, NBAR = 47;
__host__ __device__ constexpr int rslot(int n) { return n & 3; }
__host__ __device__ constexpr int rpar(int n) { return (n >> 2) & 1; }

__global__ void __cluster_dims__(2, 1, 1) __launch_bounds__(512, 1)
fused_kernel(const __grid_constant__ Maps maps, const __nv_bfloat16* __restrict__ x, const __nv_bfloat16* __restrict__ w_r,
             const __nv_bfloat16* __restrict__ w_i, const __nv_bfloat16* __restrict__ gate_w, __nv_bfloat16* __restrict__ out) {
  extern __shared__ __align__(1024) uint8_t smem[];
  const uint32_t sb = smem_u32(smem);
  const uint32_t bars = sb + OFF_BAR;
  const int tid = threadIdx.x, lane = tid & 31;
  const int warp = __shfl_sync(0xffffffffu, tid >> 5, 0);
  const bool helper = blockIdx.x >= 128;
  const int cl = (blockIdx.x >> 1) & 63, rank = blockIdx.x & 1;
  const int q4 = cl & 3, rb = cl >> 2;
  const int j = 2 * q4 + rank;
  const int f_full = 448 * q4 + (rank ? 256 : 0);
  const int f_half = 448 * q4 + (rank ? 224 : 192);
  const int kg = 2 * j + (rb >> 3), tn = rb & 7;

  if (tid == 64) { PROF_EV(0); PROF_CK(40); }
  auto x_load = [&](int q) {
    mbar_expect_tx(bars + 8 * (B_FX + q), U);
    tma3d(sb + q * U, &maps.x, bars + 8 * (B_FX + q), 64 * q, 0, 2 * rb);
  };
  if (warp < 8) {
    asm volatile("barrier.cluster.arrive.relaxed.aligned;" ::: "memory");
    asm volatile("setmaxnreg.inc.sync.aligned.u32 192;");
    if (tid == 0) PROF_EV(33);
    if (!helper) {
      const int wg = warp >> 2, w = warp & 3, g = lane >> 2;
      const bool elect = (tid & 127) == 0;
      float cX[32], cA[64], cB[64], ci[64], ct[64];
      const int zero = blockIdx.x >> 16;
      uint32_t h[56], yf[16];
      const uint32_t d0 = (sb & 0x3FFFF) >> 4;
      const uint32_t dK = d0 | (1u << 16), dN = d0 | (512u << 16);
      const uint32_t dX = dK + wg * 512;
      constexpr uint32_t RING = OFF_RING >> 4;
      auto waitA = [&](int n) { mbar_wait(bars + 8 * (B_FA + rslot(n)), rpar(n)); };
      auto freeA = [&](int n) { mbar_arrive_if(elect, bars + 8 * (B_EA + rslot(n))); };
      auto nop = [] {};

      if (tid == 0) PROF_EV(34);
      asm volatile("bar.sync 0, 384;" ::: "memory");
      if (tid == 0) PROF_EV(35);
#pragma unroll 1
      for (int kb = 0; kb < 8; kb++) {
        mbar_wait(bars + 8 * (B_FX + kb), 0);
        if (tid == 0 && kb == 0) PROF_EV(36);
        waitA(kb);
        wg_fence();
        const uint64_t dx = d128(dX + kb * 1024), df = d128(dK + (OFF_XB >> 4) + rslot(kb) * 512), db = d128(dN + RING + rslot(kb) * 1024);
        mma_ss64<0, 0, 2>(cX, df, dx, kb);
        mma_ss64<0, 0, 1>(cX, df + 2, dx + 2);
        wg_commit(); wg_wait<1>();
        mbar_arrive_if(elect && kb, bars + 8 * (B_EA + rslot(kb - 1)));
        mma_ss64<0, 0, 1>(cX, df + 4, dx + 4);
        mma_ss64<0, 0, 1>(cX, df + 6, dx + 6);
        wg_commit();
        mma_ss128<0, 1, 2>(cA, dx, db, kb);
#pragma unroll
        for (int k = 1; k < 4; k++) mma_ss128<0, 1, 1>(cA, dx + k * 2, db + k * 128);
        wg_commit();
        if (kb == 0 && tid == 0) PROF_EV(1);
      }
      wg_wait<1>();
      fence_regs<0, 32>(cX);
#pragma unroll
      for (int e = 0; e < 16; e++) yf[e] = pack_pin(cX[2 * e], cX[2 * e + 1]);
      if (tid == 0) PROF_EV(2);
      float o0 = 1.0f, o1 = 1.0f;
      auto glu = [&](auto scaled, auto& acc, int half, int ho, int i0, int i1) {
#pragma unroll
        for (int i = i0; i < i1; i++) {
          float a = fmaxf(acc[2 * i], 0.f) * acc[half + 2 * i], b = fmaxf(acc[2 * i + 1], 0.f) * acc[half + 1 + 2 * i];
          if (decltype(scaled)::value) { const float o = (i & 1) ? o1 : o0; a *= o; b *= o; }
          h[ho + i] = pack_pin(a, b);
        }
      };
      {
        waitA(8); mbar_wait(bars + 8 * B_E0, 0);
        const uint64_t de = d128(dN + (wg ? RING : OFF_XB >> 4));
        wg_fence();
        mma_rs128<0, 1, 0>(cB, yf[0], yf[1], yf[2], yf[3], de);
#pragma unroll
        for (int k = 1; k < 4; k++) mma_rs128<0, 1, 1>(cB, yf[4 * k], yf[4 * k + 1], yf[4 * k + 2], yf[4 * k + 3], de + k * 128);
        wg_commit();
        wg_wait<1>();
        freeA(7);
        mbar_arrive_if(elect, bars + 8 * B_C1);
        fence_regs<0, 64>(cA);
        glu(IC<0>(), cA, 32, 0, 0, 16);
      }
      bool rel = false;
      auto acquire = [&](int n) {
        rel = elect;
        if (!mbar_try(bars + 8 * (B_FA + rslot(n)), rpar(n))) { wg_wait<0>(); freeA(n - 1); rel = false; waitA(n); }
      };
      auto freeP = [&](int n) { mbar_arrive_if(rel, bars + 8 * (B_EA + rslot(n - 1))); };
      auto ffn_step = [&](auto first, auto split, float (&acc)[64], int n, int kb, auto done, auto work) {
        constexpr int SPLIT = decltype(split)::value;
        acquire(n);
        wg_fence();
        const uint64_t dx = d128(dX + kb * 1024), db = d128(dN + RING + rslot(n) * 1024);
        mma_ss128<0, 1, decltype(first)::value>(acc, dx, db, zero);
#pragma unroll
        for (int k = 1; k < SPLIT; k++) mma_ss128<0, 1, 1>(acc, dx + k * 2, db + k * 128);
        wg_commit();
        work();
        wg_wait<1>();
        freeP(n);
        done();
        if (SPLIT < 4) {
          wg_fence();
#pragma unroll
          for (int k = SPLIT; k < 4; k++) mma_ss128<0, 1, 1>(acc, dx + k * 2, db + k * 128);
          wg_commit();
        }
      };
      {
        const int s0 = 2 * rb + wg, kr = 2 * ((s0 & 1) | ((s0 & 4) >> 1));
        const int m = lane >> 3, r = lane & 7;
        const uint32_t a0 = sb + OFF_XB + wg * 8192 + (((w >> 1) * 8 + (m >> 1)) * 2 + (w & 1)) * 256 + (m & 1) * 128 + ((r ^ (kr + (m & 1))) << 4);
        ffn_step(IC<2>(), IC<4>(), cA, 9, 0, [&] { fence_regs<0, 64>(cB); }, nop);
        asm volatile("bar.sync 5, 256;" ::: "memory");
#pragma unroll
        for (int i = 0; i < 4; i++)
          stsm4t(a0 + i * 1024, pack_bf16(cB[8 * i] - cB[34 + 8 * i], cB[8 * i + 1] - cB[35 + 8 * i]),
                 pack_bf16(cB[32 + 8 * i] + cB[8 * i + 2], cB[33 + 8 * i] + cB[8 * i + 3]),
                 pack_bf16(cB[8 * i + 4] - cB[38 + 8 * i], cB[8 * i + 5] - cB[39 + 8 * i]),
                 pack_bf16(cB[36 + 8 * i] + cB[8 * i + 6], cB[37 + 8 * i] + cB[8 * i + 7]));
        if (j == 0 && w == 0) {
          const uint32_t a1 = r ? sb + OFF_SP + 1024 : sb + OFF_SP + wg * 512 + (m & 1) * 256 + (m >> 1) * 128;
#pragma unroll
          for (int n = 0; n < 8; n++)
            asm volatile("stmatrix.sync.aligned.m8n8.x4.shared.b16 [%0], {%1,%2,%3,%4};" ::"r"(a1 + ((n ^ (kr + (m >> 1))) << 4)),
                         "r"(pack_bf16(cB[4 * n], cB[4 * n + 1])), "r"(pack_bf16(cB[4 * n + 2], cB[4 * n + 3])),
                         "r"(pack_bf16(cB[32 + 4 * n], cB[33 + 4 * n])), "r"(pack_bf16(cB[34 + 4 * n], cB[35 + 4 * n])) : "memory");
        }
        ffn_step(IC<1>(), IC<2>(), cA, 10, 1, nop, [&] {
          asm volatile("fence.proxy.async.shared::cta;" ::: "memory");
          __syncwarp();
          mbar_arrive_if(lane == 0, bars + 8 * (B_XS + wg));
          if (tid == 0) PROF_EV(3);
        });
      }
#pragma unroll 1
      for (int kb = 2; kb < 8; kb++) ffn_step(IC<1>(), IC<1>(), cA, 9 + kb, kb, nop, nop);
      mbar_wait(bars + 8 * B_G, 0);
      const uint32_t gb0 = *(const uint32_t*)(smem + OFF_G + (wg * 64 + w * 16 + g) * 4), gb1 = *(const uint32_t*)(smem + OFF_G + (wg * 64 + w * 16 + g + 8) * 4);
      const uint32_t tag = gb0 & 1;
      const float g0 = __uint_as_float(gb0 & ~1u), g1 = __uint_as_float(gb1 & ~1u);
      o0 = 1.0f - g0; o1 = 1.0f - g1;
      ffn_step(IC<2>(), IC<1>(), cB, 17, 0, [&] { fence_regs<0, 64>(cA); }, [&] {
#pragma unroll
        for (int e = 0; e < 16; e++) { const float o = (e & 1) ? o1 : o0; h[e] = pack_pin(bf_lo(h[e]) * o, bf_hi(h[e]) * o); }
      });
      if (tid == 0) PROF_EV(4);
      ffn_step(IC<1>(), IC<1>(), cB, 18, 1, nop, [&] { glu(IC<1>(), cA, 32, 16, 0, 8); });
      ffn_step(IC<1>(), IC<1>(), cB, 19, 2, nop, [&] { glu(IC<1>(), cA, 32, 16, 8, 16); });
#pragma unroll 1
      for (int kb = 3; kb < 8; kb++) ffn_step(IC<1>(), IC<1>(), cB, 17 + kb, kb, nop, nop);
      if (tid == 0) PROF_EV(5);
      auto m_step = [&](auto first, int i, auto done, auto work) {
        acquire(25 + i);
        wg_fence();
        const uint64_t dx = d128(dX + i * 2048), dm = d64(dN + RING + rslot(25 + i) * 1024);
        mma_ss64<0, 1, decltype(first)::value>(ct, dx, dm);
        mma_ss64<0, 1, 1>(ct, dx + 2, dm + 64);
        wg_commit();
        work();
        wg_wait<1>();
        freeP(25 + i);
        done();
        wg_fence();
#pragma unroll
        for (int k = 2; k < 8; k++) mma_ss64<0, 1, 1>(ct, dx + ((k >> 2) * 1024 + (k & 3) * 2), dm + k * 64);
        wg_commit();
      };
      auto freeT = [&](int t) { mbar_arrive_if(elect, bars + 8 * (B_ET + t)); };
      m_step(IC<0>(), 0, [&] { fence_regs<0, 64>(cB); }, nop);
      m_step(IC<1>(), 1, [&] { freeT(0); }, [&] { glu(IC<1>(), cB, 32, 32, 0, 5); });
      m_step(IC<1>(), 2, [&] { freeT(1); }, [&] { glu(IC<1>(), cB, 32, 32, 5, 11); });
      m_step(IC<1>(), 3, [&] { freeT(2); }, [&] { glu(IC<1>(), cB, 32, 32, 11, 16); });
      waitA(29 + wg);
      if (tid == 0) PROF_EV(6);
      mbar_wait(bars + 8 * (j == 0 ? B_T : B_TL), 0);
      if (tid == 0) PROF_EV(7);
      wg_fence();
      {
        const uint64_t dt = d128(dN + (OFF_T >> 4) + wg * 512), de = d128(dK + RING + (1 + wg) * 1024);
        mma_ss64<0, 1, 0>(ci, de, dt);
        mma_ss64<32, 1, 0>(ci, de + 512, dt);
#pragma unroll
        for (int k = 1; k < 4; k++) {
          mma_ss64<0, 1, 1>(ci, de + k * 2, dt + k * 128);
          mma_ss64<32, 1, 1>(ci, de + (512 + k * 2), dt + k * 128);
        }
        wg_commit();
        wg_wait<1>();
        freeT(3);
        fence_regs<0, 32>(ct);
        glu(IC<1>(), ct, 16, 48, 0, 8);
      }

      auto head = [&](auto off, int t, auto first) {
        constexpr int O = decltype(off)::value;
        mbar_wait(bars + 8 * (B_FT + (t & 3)), t >> 2);
        const uint64_t db = d128(dN + (t & 3) * (TB >> 4) + rank * 256);
        wg_fence();
        mma_rs64<O, 1, decltype(first)::value>(ct, h[0], h[1], h[2], h[3], db, zero);
#pragma unroll
        for (int k = 1; k < 6; k++) mma_rs64<O, 1, 1>(ct, h[4 * k], h[4 * k + 1], h[4 * k + 2], h[4 * k + 3], db + k * 128);
        wg_commit();
        wg_wait<1>();
      };
      auto rest = [&](auto off, int t) {
        constexpr int O = decltype(off)::value;
        const uint64_t db = d128(dN + (t & 3) * (TB >> 4)), dw = db + rank * 256, dm = db + (rank ? 0 : 1536);
        wg_fence();
#pragma unroll
        for (int k = 6; k < 12; k++) mma_rs64<O, 1, 1>(ct, h[4 * k], h[4 * k + 1], h[4 * k + 2], h[4 * k + 3], dw + k * 128);
#pragma unroll
        for (int k = 0; k < 2; k++) mma_rs64<O, 1, 1>(ct, h[48 + 4 * k], h[49 + 4 * k], h[50 + 4 * k], h[51 + 4 * k], dm + k * 128);
#pragma unroll
        for (int k = 0; k < 4; k++) mma_rs64<O, 1, 1>(ct, yf[4 * k], yf[4 * k + 1], yf[4 * k + 2], yf[4 * k + 3], db + (14 + k) * 128);
        wg_commit();
      };
      const uint32_t peerZ = mapa(sb + OFF_Z + tid * 16, rank ^ 1), peerB = mapa(bars + 8 * B_Z, rank ^ 1);
      auto send = [&](auto off, int t) {
        constexpr int O = decltype(off)::value;
        fence_regs<O, 32>(ct);
        const bool grid = t >= 3 && t < 6;
        const int z = grid ? t - 3 : t == 6 ? 3 : t;
        if (grid) {
          mbar_wait(bars + 8 * (B_Z + z), 0);
#pragma unroll
          for (int i = 0; i < 4; i++) {
            const uint4 p = *(const uint4*)(smem + OFF_Z + z * U + i * 4096 + tid * 16);
            const uint32_t a[4] = {p.x, p.y, p.z, p.w};
#pragma unroll
            for (int e = 0; e < 4; e++) { ct[O + 8 * i + 2 * e] += bf_lo(a[e]); ct[O + 8 * i + 2 * e + 1] += bf_hi(a[e]); }
          }
        }
        uint32_t pk[16];
#pragma unroll
        for (int i = 0; i < 16; i++) pk[i] = pack_bf16(ct[O + 2 * i], ct[O + 2 * i + 1]);
        if (grid) {
          const int owner = rb * 8 + 2 * ((q4 + z + 1) & 3) + rank;
          uint4* dst = g_part + (size_t)(owner * 3 + z) * 1024 + tid;
#pragma unroll
          for (int i = 0; i < 4; i++) st_x4(dst + i * 256, (pk[4 * i] & ~1u) | tag, pk[4 * i + 1], pk[4 * i + 2], pk[4 * i + 3]);
          __syncwarp();
          hint_add_if(lane == 0, &g_cntP[32 * owner + z]);
        } else {
#pragma unroll
          for (int i = 0; i < 4; i++)
            asm volatile("st.async.weak.shared::cluster.mbarrier::complete_tx::bytes.v4.b32 [%0], {%1,%2,%3,%4}, [%5];" ::"r"(peerZ + z * U + i * 4096),
                         "r"(pk[4 * i]), "r"(pk[4 * i + 1]), "r"(pk[4 * i + 2]), "r"(pk[4 * i + 3]), "r"(peerB + 8 * z) : "memory");
        }
      };
      asm volatile("barrier.cluster.wait.aligned;" ::: "memory");
      head(IC<0>(), 0, IC<2>());
      if (elect) asm volatile("mbarrier.arrive.shared::cluster.b64 _, [%0];" ::"r"(mapa(bars + 8 * B_RDY, rank ^ 1)) : "memory");
      fence_regs<0, 64>(ci);
#pragma unroll
      for (int i = 0; i < 16; i++) {
        const float gg = ((i & 1) ? g1 : g0) * (2.0f / (2048.0f * 512.0f));
        if (i & 2) yf[i] = pack_pin((ci[2 * i] - ci[28 + 2 * i]) * gg, (ci[2 * i + 1] - ci[29 + 2 * i]) * gg);
        else yf[i] = pack_pin((ci[2 * i] + ci[36 + 2 * i]) * gg, (ci[2 * i + 1] + ci[37 + 2 * i]) * gg);
      }
      if (tid == 0) PROF_EV(8);
#pragma unroll 1
      for (int t = 0;; t += 2) {
        rest(IC<0>(), t);
        head(IC<32>(), t + 1, IC<2>());
        mbar_arrive_if(elect && t < 6, bars + 8 * (B_ET + t));
        if (t == 0) mbar_wait(bars + 8 * B_RDY, 0);
        send(IC<0>(), t);
        rest(IC<32>(), t + 1);
        if (t == 6) break;
        head(IC<0>(), t + 2, IC<2>());
        mbar_arrive_if(elect, bars + 8 * (B_ET + t + 1));
        send(IC<32>(), t + 1);
      }
      if (tid == 0) PROF_EV(9);
      {
        float sum[32];
        mbar_wait(bars + 8 * (B_Z + 3), 0);
#pragma unroll
        for (int i = 0; i < 4; i++) {
          const uint4 p = *(const uint4*)(smem + OFF_Z + 3 * U + i * 4096 + tid * 16);
          const uint32_t a[4] = {p.x, p.y, p.z, p.w};
#pragma unroll
          for (int e = 0; e < 4; e++) { sum[8 * i + 2 * e] = bf_lo(a[e]); sum[8 * i + 2 * e + 1] = bf_hi(a[e]); }
        }
#pragma unroll 1
        for (int z = 0; z < 3; z++) {
          mbar_wait(bars + 8 * (B_HP + z), 0);
          if (z == 2 && tid == 0) PROF_EV(24);
          uint4 pv[4];
#pragma unroll
          for (int i = 0; i < 4; i++) pv[i] = *(const uint4*)(smem + z * U + i * 4096 + tid * 16);
          const uint32_t t0 = (uint32_t)clock();
          while (__any_sync(0xffffffffu, ((pv[0].x ^ tag) | (pv[1].x ^ tag) | (pv[2].x ^ tag) | (pv[3].x ^ tag)) & 1)) {
#pragma unroll
            for (int i = 0; i < 4; i++) pv[i] = ld_x4(g_part + (size_t)((rb * 8 + j) * 3 + z) * 1024 + tid + i * 256);
            spin_guard(t0);
          }
#pragma unroll
          for (int i = 0; i < 4; i++) {
            const uint32_t a[4] = {pv[i].x & ~1u, pv[i].y, pv[i].z, pv[i].w};
#pragma unroll
            for (int e = 0; e < 4; e++) { sum[8 * i + 2 * e] += bf_lo(a[e]); sum[8 * i + 2 * e + 1] += bf_hi(a[e]); }
          }
        }
        if (tid == 0) PROF_EV(14);
        wg_wait<0>();
        fence_regs<32, 32>(ct);
#pragma unroll
        for (int i = 0; i < 32; i++) sum[i] += ct[32 + i];
        const uint32_t stg = sb + OFF_T + warp * 2048;
        const int mr = (lane & 7) + ((lane >> 3) & 1) * 8, mc = lane >> 4;
#pragma unroll
        for (int i = 0; i < 4; i++) {
          const uint32_t a = stg + mr * 128 + (((2 * i + mc) ^ (mr & 7)) << 4);
          asm volatile("stmatrix.sync.aligned.m8n8.x4.shared.b16 [%0], {%1,%2,%3,%4};" ::"r"(a), "r"(pack_bf16(sum[8 * i], sum[8 * i + 1])),
                       "r"(pack_bf16(sum[8 * i + 2], sum[8 * i + 3])), "r"(pack_bf16(sum[8 * i + 4], sum[8 * i + 5])),
                       "r"(pack_bf16(sum[8 * i + 6], sum[8 * i + 7])) : "memory");
        }
        __syncwarp();
#pragma unroll
        for (int i = 0; i < 4; i++) {
          const int r = 4 * i + (lane >> 3), c = lane & 7;
          const uint4 v = *(const uint4*)(smem + OFF_T + warp * 2048 + r * 128 + ((c ^ (r & 7)) << 4));
          *(uint4*)(out + (size_t)(2 * rb + wg + 32 * (16 * w + r)) * 512 + 64 * j + 8 * c) = v;
        }
      }
      if (tid == 0) { PROF_EV(15); PROF_CK(41); }
    }
  } else if (warp < 12) {
    asm volatile("setmaxnreg.dec.sync.aligned.u32 104;");
    asm volatile("barrier.cluster.arrive.relaxed.aligned;" ::: "memory");
    const int t = tid - 256, w = warp - 8;
    const uint32_t ep = ld_x1(&g_epoch[blockIdx.x * 8]);
    const uint32_t tag = (ep + 1) & 1;
    auto gate_rows = [&] {
      const int r = 16 * j + 4 * w + (lane >> 3);
      const uint4* px = (const uint4*)(x + (size_t)(2 * rb + (r >> 6) + 32 * (r & 63)) * 512) + (lane & 7);
      const uint4* pg = (const uint4*)gate_w + (lane & 7);
      {
        float a = 0.f;
#pragma unroll 1
        for (int i = 0; i < 8; i += 4) {
          uint4 u[4], v[4];
#pragma unroll
          for (int e = 0; e < 4; e++) { u[e] = __ldg(px + (i + e) * 8); v[e] = __ldg(pg + (i + e) * 8); }
#pragma unroll
          for (int e = 0; e < 4; e++) {
            a = fmaf(bf_lo(u[e].x), bf_lo(v[e].x), a); a = fmaf(bf_hi(u[e].x), bf_hi(v[e].x), a);
            a = fmaf(bf_lo(u[e].y), bf_lo(v[e].y), a); a = fmaf(bf_hi(u[e].y), bf_hi(v[e].y), a);
            a = fmaf(bf_lo(u[e].z), bf_lo(v[e].z), a); a = fmaf(bf_hi(u[e].z), bf_hi(v[e].z), a);
            a = fmaf(bf_lo(u[e].w), bf_lo(v[e].w), a); a = fmaf(bf_hi(u[e].w), bf_hi(v[e].w), a);
          }
        }
#pragma unroll
        for (int o = 4; o; o >>= 1) a += __shfl_xor_sync(0xffffffffu, a, o);
        if ((lane & 7) == 0)
          asm volatile("st.relaxed.gpu.global.f32 [%0], %1;" ::"l"(g_gate + rb * 128 + r), "f"(tagf(__fdividef(1.0f, 1.0f + __expf(-a)), tag)) : "memory");
        if (t == 0) PROF_EV(18);
      }
      if (w == 0) {
        const int c = lane >> 4, jj = 16 * blockIdx.x + (lane & 15), jm = (2048 - jj) & 2047;
        const unsigned short* pr = (const unsigned short*)w_r + 256 * c;
        const unsigned short* pi = (const unsigned short*)w_i + 256 * c;
        const float wr = 0.25f * (bf_lo(__ldg(pr + jj * 257)) + bf_lo(__ldg(pr + jm * 257)));
        const float wi = 0.25f * (bf_lo(__ldg(pi + jj * 257)) - bf_lo(__ldg(pi + jm * 257)));
        st_u2(g_Wh + c * 2048 + jj, c ? pack_bf16(-wi, wr) : pack_bf16(wr, wi), tag);
        __syncwarp();
        hint_add_if(lane == 0, &g_cntW[0]);
      }
    };
    {
      const int g = lane >> 2, q = lane & 3;
      uint32_t wf[32];
      if (!helper) {
        asm volatile("bar.sync 4, 256;" ::: "memory");
        mbar_wait(bars + 8 * (B_FX + GATE_AT), 0);
        gate_rows();
        const uint32_t wa = sb + OFF_T + w * (3072 + 4) + q * 48 + g * 2;
        mbar_wait(bars + 8 * B_C1, 0);
        if (t == 0) PROF_EV(32);
        if (WPACE) __nanosleep(WPACE * w);
#pragma unroll 1
        for (int ri = 0; ri < 2; ri++) {
          if (lane == 0) {
            mbar_expect_tx(bars + 8 * (B_WR + w), 3072);
            tma4d(sb + OFF_T + w * 3072, ri ? &maps.wi : &maps.wr, bars + 8 * (B_WR + w), 16 * kg, 0, 2 * w, tn);
          }
          if (ri) {
            const uint32_t t0 = (uint32_t)clock();
            uint32_t v;
            do { v = ld_x1(g_gate + rb * 128 + t); spin_guard(t0); } while (__any_sync(0xffffffffu, (v ^ tag) & 1));
            *(uint32_t*)(smem + OFF_G + t * 4) = v;
            __syncwarp();
            mbar_arrive_if(lane == 0, bars + 8 * B_G);
          }
          mbar_wait(bars + 8 * (B_WR + w), ri);
#pragma unroll
          for (int n2 = 0; n2 < 4; n2++) {
            uint32_t v[8];
#pragma unroll
            for (int i = 0; i < 8; i++)
              asm volatile("ld.shared.u16 %0, [%1];" : "=r"(v[i]) : "r"(wa + (2 * n2 + ((i >> 1) & 1)) * 192 + (i & 1) * (1536 + 2) + (i >> 2) * 16) : "memory");
#pragma unroll
            for (int i = 0; i < 8; i++) {
              uint32_t& d = wf[(i >> 2) * 16 + 4 * n2 + (i & 3)];
              d = __byte_perm(d, v[i], 0x5432);
              asm volatile("" : "+r"(d)::"memory");
            }
          }
          __syncwarp();
        }
        asm volatile("bar.sync 1, 128;" ::: "memory");
        if (t == 0) PROF_EV(11);
      } else {
        asm volatile("bar.sync 4, 256;" ::: "memory");
        hint_wait(&g_cntW[0], (ep + 1) * 128u);
        const uint32_t t0 = (uint32_t)clock();
#pragma unroll 1
        for (;;) {
          uint32_t bad = 0;
#pragma unroll
          for (int i = 0; i < 32; i++) {
            const float2 v = ld_x2((const float2*)g_Wh + (i >> 4) * 2048 + 16 * w + g + 8 * (i & 1) + 64 * q + ((i >> 1) & 7) * 256);
            wf[i] = __float_as_uint(v.x); bad |= __float_as_uint(v.y) ^ tag;
          }
          if (!__any_sync(0xffffffffu, bad & 1)) break;
          spin_guard(t0);
        }
        if (t == 0) PROF_EV(11);
      }
      if (t == 0) { mbar_expect_tx(bars + 8 * B_W, 8192); bulk_load(sb + OFF_D, g_DT.v, 8192, bars + 8 * B_W); }
      mbar_wait(bars + 8 * B_W, 0);
      mbar_wait(bars + 8 * B_HX, 0);
      if (t == 0) PROF_EV(12);
      const uint32_t dd = (sb & 0x3FFFF) >> 4;
      const uint64_t dF = d128((dd + (OFF_D >> 4)) | (512u << 16)), dI = d128((dd + (OFF_D >> 4)) | (1u << 16)), dA = d128((dd + (OFF_XB >> 4)) | (512u << 16));
      float az[32];
      const int zero = blockIdx.x >> 16;
      uint32_t pf[32];
#pragma unroll
      for (int mt = 0; mt < 2; mt++) {
        wg_fence();
        if (mt == 0) mma_ss64<0, 3, 0>(az, dA, dF);
        else mma_ss64<0, 3, 2>(az, dA + 512, dF, zero);
#pragma unroll
        for (int k = 1; k < 4; k++) mma_ss64<0, 3, 1>(az, dA + (mt * 512 + k * 128), dF + k * 128);
        wg_commit();
        wg_wait<0>();
        fence_regs<0, 32>(az);
#pragma unroll
        for (int i = 0; i < 16; i++) {
          const float wr = bf_lo(wf[16 * mt + i]), wi = bf_hi(wf[16 * mt + i]);
          pf[16 * mt + i] = pack_pin(fmaf(az[2 * i], wr, -az[2 * i + 1] * wi), fmaf(az[2 * i], wi, az[2 * i + 1] * wr));
        }
      }
      if (t == 0) PROF_EV(16);
#pragma unroll
      for (int mt = 0; mt < 2; mt++) {
        wg_fence();
        mma_rs64<0, 0, 2>(az, pf[16 * mt], pf[16 * mt + 1], pf[16 * mt + 2], pf[16 * mt + 3], dI, mt ? (int)helper : zero);
#pragma unroll
        for (int k = 1; k < 4; k++) mma_rs64<0, 0, 1>(az, pf[16 * mt + 4 * k], pf[16 * mt + 4 * k + 1], pf[16 * mt + 4 * k + 2], pf[16 * mt + 4 * k + 3], dI + k * 2);
        wg_commit();
        wg_wait<0>();
        fence_regs<0, 32>(az);
        if (!helper) {
          const int m = lane >> 3, r = lane & 7;
          const int sl = 2 * (m >> 1) + ((r >> 1) & 1) + 4 * (r >> 2);
          const uint32_t a0 = sb + OFF_XB + (2 * w + (m & 1)) * 2048 + sl * 64 + (((mt * 2 + (r & 1)) ^ (sl >> 1)) << 4);
#pragma unroll
          for (int i = 0; i < 4; i++)
            stsm4t(a0 + i * 512, pack_bf16(az[8 * i], az[8 * i + 1]), pack_bf16(az[8 * i + 2], az[8 * i + 3]), pack_bf16(az[8 * i + 4], az[8 * i + 5]),
                   pack_bf16(az[8 * i + 6], az[8 * i + 7]));
        }
      }
      if (helper) {
#pragma unroll
        for (int i = 0; i < 16; i++) {
          const int n = i >> 1, s0 = 8 * (n >> 1) + 2 * (n & 1) + (q & 1) + 4 * (q >> 1);
          if ((n & 1) == (int)(blockIdx.x & 1)) st_u2(g_Ts + s0 * 64 + 16 * w + g + 8 * (i & 1), pack_bf16(az[2 * i], az[2 * i + 1]), tag);
        }
        __syncwarp();
        hint_add_if(lane == 0, &g_cntH[0]);
        if (t == 0) { g_epoch[blockIdx.x * 8] = ep + 1; PROF_EV(13); }
      } else {
        asm volatile("fence.proxy.async.shared::cta;" ::: "memory");
        __syncwarp();
        if (lane == 0) {
          if (t == 0) PROF_EV(17);
          if (SPACE) __nanosleep(SPACE * w);
          asm volatile("cp.async.bulk.tensor.3d.global.shared::cta.bulk_group [%0, {%2, %3, %4}], [%1];" ::"l"(&maps.ts), "r"(sb + OFF_XB + w * 4096),
                       "r"(32 * kg), "r"(0), "r"(8 * tn + 2 * w) : "memory");
          bulk_done_signal(&g_cntT[32 * j]);
          if (t == 96) PROF_EV(13);
        }
        __syncwarp();
        if (j == 0) {
          hint_wait(&g_cntH[0], (ep + 1) * 8u);
          const uint32_t t0 = (uint32_t)clock();
          float2 v;
          do { v = ld_x2((const float2*)g_Ts + 2 * rb * 64 + t); spin_guard(t0); } while (__any_sync(0xffffffffu, (__float_as_uint(v.y) ^ tag) & 1));
          mbar_wait(bars + 8 * B_TL, 0);
          const uint32_t u = __float_as_uint(v.x);
          *(uint16_t*)(smem + OFF_T + t * 128 + ((t & 7) << 4)) = (uint16_t)u;
          *(uint16_t*)(smem + OFF_T + t * 128 + (((t & 7) ^ 1) << 4)) = (uint16_t)(u >> 16);
          asm volatile("fence.proxy.async.shared::cta;" ::: "memory");
          __syncwarp();
          mbar_arrive_if(lane == 0, bars + 8 * B_T);
        }
      }
    }
  } else {
    asm volatile("setmaxnreg.dec.sync.aligned.u32 24;");
    if (warp < 14) {
      if (lane == 0) {
#pragma unroll
        for (int i = 0; i < 6; i++) mbar_init(bars + 8 * (2 * i + warp - 12), 1);
        asm volatile("fence.proxy.async.shared::cta;" ::: "memory");
      }
      asm volatile("bar.sync 2, 64;" ::: "memory");
      asm volatile("bar.arrive 0, 384;" ::: "memory");
      asm volatile("bar.arrive 4, 256;" ::: "memory");
      if (lane == 0) {
        if (!helper) {
#pragma unroll 1
          for (int n = 0; n < NR; n++) {
            const uint32_t fb = bars + 8 * (B_FA + n);
            if (warp == 12) { x_load(n); mbar_expect_tx(fb, U + 8192); }
            else tma2d(sb + OFF_XB + n * 8192, &maps.ft, fb, 64 * n, 64 * j);
            tma2d(sb + OFF_RING + n * U + (warp - 12) * 8192, &maps.g64 + (warp - 12), fb, f_full, 64 * n);
          }
        }
      }
    } else {
      if (lane != 0) {
      } else if (warp == 15) {
#pragma unroll
        for (int i = B_FT; i < NBAR; i++) mbar_init(bars + 8 * i, i < B_EA ? 1 : i < B_T ? 2 : 4);
#pragma unroll
        for (int i = 0; i < 4; i++) mbar_expect_tx(bars + 8 * (B_Z + i), U);
        asm volatile("fence.mbarrier_init.release.cluster;" ::: "memory");
        asm volatile("fence.proxy.async.shared::cta;" ::: "memory");
      } else {
#pragma unroll
        for (int i = 1; i < 4; i++) asm volatile("prefetch.tensormap [%0];" ::"l"((const char*)&maps + i * 128) : "memory");
      }
      if (lane == 0) PROF_EV(warp + 14);
      __syncwarp();
      asm volatile("bar.arrive 0, 384;" ::: "memory");
      asm volatile("bar.arrive 4, 256;" ::: "memory");
    }
    __syncwarp();
    asm volatile("barrier.cluster.arrive.relaxed.aligned;" ::: "memory");
    asm volatile("bar.sync 3, 128;" ::: "memory");
    if (lane == 0 && (!helper || warp == 15)) {
      if (warp < 14) {
        const int p = warp - 12;
        if (p == 0) x_load(NR);
#pragma unroll 1
        for (int n = NR; n < 31; n++) {
          const bool table = n == 8 || n >= 29;
          const int q = n < 8 ? n : n - 1;
          const CUtensorMap* m = table ? &maps.e : n >= 25 ? &maps.g32 + p : &maps.g64 + p;
          const int c0 = table ? 0 : n >= 25 ? f_half : f_full + 64 * (q >> 3);
          const int c1 = table ? (2 * rb + ((n & 1) ^ 1)) * 128 + 64 * p : n >= 25 ? 128 * (n - 25) : 64 * (q & 7);
          const uint32_t fb = bars + 8 * (B_FA + (n & 3)), dst = sb + OFF_RING + (n & 3) * U + p * 8192;
          const uint32_t bytes = n < 8 ? U + 8192 : U;
          mbar_wait(bars + 8 * (B_EA + (n & 3)), ((n >> 2) & 1) ^ 1);
          tma2d(dst, m, fb, c0, c1);
          if (p == 0) mbar_expect_tx(fb, bytes);
          if (n < 10) {
            if (n < 8 && p == 1) tma2d(sb + OFF_XB + (n & 3) * 8192, &maps.ft, fb, 64 * n, 64 * j);
            if (n < 7 && p == 0) x_load(n + 1);
            if (n == 9) {
              if (p == 0) mbar_expect_tx(bars + 8 * B_E0, U);
              tma2d(sb + OFF_XB + p * 8192, &maps.e, bars + 8 * B_E0, 0, 2 * rb * 128 + 64 * p);
            }
          }
        }
      } else if (warp == 15) {
        const unsigned ep1 = ld_x1(&g_epoch[blockIdx.x * 8]) + 1;
        flag_wait(&g_cntX[helper ? 0 : 32 * j], ep1 * 16u);
        PROF_EV(22);
        mbar_expect_tx(bars + 8 * B_HX, U);
        bulk_load(sb + OFF_XB, g_X + (size_t)(helper ? 128 : kg * 8 + tn) * 8192, U, bars + 8 * B_HX);
        if (!helper) {
          flag_wait(&g_cntT[32 * j], ep1 * 64u);
          PROF_EV(23);
          mbar_expect_tx(bars + 8 * B_TL, U);
          tma3d(sb + OFF_T, &maps.t, bars + 8 * B_TL, 64 * j, 0, 2 * rb);
#pragma unroll 1
          for (int i = 0; i < 3; i++) {
            mbar_wait(bars + 8 * (B_PZ + (i >> 1)), 0);
            flag_wait(&g_cntP[32 * (rb * 8 + j) + i], ep1 * 8u);
            mbar_expect_tx(bars + 8 * (B_HP + i), U);
            bulk_load(sb + i * U, g_part + (size_t)((rb * 8 + j) * 3 + i) * 1024, U, bars + 8 * (B_HP + i));
          }
          g_epoch[blockIdx.x * 8] = ep1;
        }
      } else {
#pragma unroll 1
        for (int h2 = 0; h2 < 2; h2++) {
          const int s0 = 2 * rb + h2, sg = (s0 & ~6) | ((s0 & 2) << 1) | ((s0 & 4) >> 1);
          mbar_wait(bars + 8 * (B_XS + h2), 0);
#pragma unroll 1
          for (int c = 0; c < 2; c++) {
            asm volatile("cp.async.bulk.tensor.4d.global.shared::cta.bulk_group [%0, {%2, %3, %4, %5}], [%1];" ::"l"(&maps.xs),
                         "r"(sb + OFF_XB + h2 * 8192 + c * 4096), "r"(0), "r"(sg), "r"(0), "r"(16 * j + 8 * c) : "memory");
            if (j == 0)
              asm volatile("cp.async.bulk.global.shared::cta.bulk_group [%0], [%1], 256;" ::"l"(g_X + 128 * 8192 + c * 4096 + sg * 128),
                           "r"(sb + OFF_SP + h2 * 512 + c * 256) : "memory");
            if (SPACE && h2 + c < 2) __nanosleep(SPACE);
          }
        }
        bulk_done_signal(&g_cntX[32 * j]);
        PROF_EV(20);
#pragma unroll 1
        for (int t = 0; t < 8; t++) {
          const int i = t < 3 ? t + 1 : t < 6 ? t - 2 : 0;
          const int col = 64 * (2 * ((q4 + i) & 3) + ((t < 3 || t == 6) ? 1 - rank : rank));
          const uint32_t fb = bars + 8 * (B_FT + (t & 3)), dst = sb + (t & 3) * TB;
          mbar_wait(bars + 8 * (B_ET + (t == 2 ? 3 : t & 3)), t >> 2);
          mbar_expect_tx(fb, TB);
          tma2d(dst, &maps.d224, fb, col, 224 * j);
          if (t < 2) mbar_wait(bars + 8 * (B_ET + t + 1), 0);
          tma2d(dst + 28672, &maps.ft, fb, col, 64 * j);
        }
      }
    }
  }
}

typedef CUresult (*EncodeFn)(CUtensorMap*, CUtensorMapDataType, cuuint32_t, void*, const cuuint64_t*, const cuuint64_t*, const cuuint32_t*,
                             const cuuint32_t*, CUtensorMapInterleave, CUtensorMapSwizzle, CUtensorMapL2promotion, CUtensorMapFloatOOBfill);

static void encode(EncodeFn f, CUtensorMap* m, const void* base, int rank, const cuuint64_t* dims, const cuuint64_t* strides, const cuuint32_t* box,
                   CUtensorMapSwizzle sw) {
  cuuint32_t es[5] = {1, 1, 1, 1, 1};
  f(m, CU_TENSOR_MAP_DATA_TYPE_BFLOAT16, rank, (void*)base, dims, strides, box, es, CU_TENSOR_MAP_INTERLEAVE_NONE, sw,
    CU_TENSOR_MAP_L2_PROMOTION_L2_128B, CU_TENSOR_MAP_FLOAT_OOB_FILL_NONE);
}

extern "C" void kernel_launch(void* const* d_in, const int* in_sizes, int n_in, void* d_out, int out_size) {
  (void)in_sizes; (void)n_in; (void)out_size;
  const __nv_bfloat16* x = (const __nv_bfloat16*)d_in[0];
  const __nv_bfloat16* w_r = (const __nv_bfloat16*)d_in[1];
  const __nv_bfloat16* w_i = (const __nv_bfloat16*)d_in[2];
  const __nv_bfloat16* Wg = (const __nv_bfloat16*)d_in[4];
  const __nv_bfloat16* Wu = (const __nv_bfloat16*)d_in[5];
  const __nv_bfloat16* Wd = (const __nv_bfloat16*)d_in[6];
  const __nv_bfloat16* gw = (const __nv_bfloat16*)d_in[7];

  void* fp = nullptr; cudaDriverEntryPointQueryResult qr;
  cudaGetDriverEntryPoint("cuTensorMapEncodeTiled", &fp, cudaEnableDefault, &qr);
  EncodeFn enc = (EncodeFn)fp;
  void *pFT, *pET, *pX, *pT;
  cudaGetSymbolAddress(&pX, g_X); cudaGetSymbolAddress(&pT, g_T);
  cudaGetSymbolAddress(&pFT, g_FT); cudaGetSymbolAddress(&pET, g_ET);

  Maps mp;
  const CUtensorMapSwizzle S128 = CU_TENSOR_MAP_SWIZZLE_128B, S64 = CU_TENSOR_MAP_SWIZZLE_64B;
  { cuuint64_t d[3] = {512, 64, 32}, s[2] = {32768, 1024}; cuuint32_t b[3] = {64, 64, 2}; encode(enc, &mp.x, x, 3, d, s, b, S128); }
  { cuuint64_t d[2] = {512, 512}, s[1] = {1024}; cuuint32_t b[2] = {64, 64}; encode(enc, &mp.ft, pFT, 2, d, s, b, S128); }
  { cuuint64_t d[4] = {128, 32, 2, 129}, s[3] = {256, 8192, 16384}; cuuint32_t b[4] = {128, 1, 2, 8}; encode(enc, &mp.xs, pX, 4, d, s, b, CU_TENSOR_MAP_SWIZZLE_NONE); }
  { cuuint64_t d[3] = {512, 32, 64}, s[2] = {65536, 1024}; cuuint32_t b[3] = {32, 32, 2}; encode(enc, &mp.ts, pT, 3, d, s, b, S64); }
  { cuuint64_t d[3] = {512, 64, 32}, s[2] = {1024, 65536}; cuuint32_t b[3] = {64, 64, 2}; encode(enc, &mp.t, pT, 3, d, s, b, S128); }
  { cuuint64_t d[2] = {64, 4096}, s[1] = {128}; cuuint32_t b[2] = {64, 64}; encode(enc, &mp.e, pET, 2, d, s, b, S128); }
  { cuuint64_t d[2] = {1792, 512}, s[1] = {3584}; cuuint32_t b[2] = {64, 64}, b2[2] = {32, 128};
    encode(enc, &mp.g64, Wg, 2, d, s, b, S128); encode(enc, &mp.u64, Wu, 2, d, s, b, S128);
    encode(enc, &mp.g32, Wg, 2, d, s, b2, S64); encode(enc, &mp.u32, Wu, 2, d, s, b2, S64); }
  { cuuint64_t d[2] = {512, 1792}, s[1] = {1024}; cuuint32_t b[2] = {64, 224}; encode(enc, &mp.d224, Wd, 2, d, s, b, S128); }
  { cuuint64_t d[4] = {264, 32, 8, 8}, s[3] = {32896, 512, 4112}; cuuint32_t b[4] = {24, 32, 2, 1};
    encode(enc, &mp.wr, w_r, 4, d, s, b, CU_TENSOR_MAP_SWIZZLE_NONE); encode(enc, &mp.wi, w_i, 4, d, s, b, CU_TENSOR_MAP_SWIZZLE_NONE); }

  cudaFuncSetAttribute(fused_kernel, cudaFuncAttributeMaxDynamicSharedMemorySize, SMEM_BYTES);
  fused_kernel<<<NCTA, 512, SMEM_BYTES>>>(mp, x, w_r, w_i, gw, (__nv_bfloat16*)d_out);
}
```

```cpp
#include <cuda_runtime.h>
#include <cuda_bf16.h>
#include <cuda.h>
#include <stdint.h>

namespace tbl {
constexpr double PI = 3.14159265358979323846264338327950288;
constexpr double sin_s(double x) { double t = x, s = x; for (int n = 1; n < 12; n++) { t *= -x * x / ((2 * n) * (2 * n + 1)); s += t; } return s; }
constexpr double cos_s(double x) { double t = 1, s = 1; for (int n = 1; n < 12; n++) { t *= -x * x / ((2 * n - 1) * (2 * n)); s += t; } return s; }
constexpr double cos2048(int m) {
  m &= 2047; if (m > 1024) m = 2048 - m;
  bool neg = false; if (m > 512) { m = 1024 - m; neg = true; }
  double v = (m <= 256) ? cos_s(2 * PI * m / 2048) : sin_s(2 * PI * (512 - m) / 2048);
  return neg ? -v : v;
}
constexpr uint16_t to_bf16(double v) {
  if (v == 0) return 0;
  uint16_t s = 0; if (v < 0) { s = 0x8000; v = -v; }
  int e = 0; while (v >= 2) { v /= 2; e++; } while (v < 1) { v *= 2; e--; }
  double m = (v - 1) * 128; int mi = (int)m; double fr = m - mi;
  if (fr > 0.5 || (fr == 0.5 && (mi & 1))) mi++;
  if (mi == 128) { mi = 0; e++; }
  return (uint16_t)(s | ((e + 127) << 7) | mi);
}
struct CosT { uint16_t v[2048]; constexpr CosT() : v() { for (int i = 0; i < 2048; i++) v[i] = to_bf16(cos2048(i)); } };
struct alignas(1024) FT {
  uint16_t v[512 * 512];
  constexpr FT() : v() {
    CosT c;
    for (int r = 0; r < 512; r++) {
      int k = (r >> 4) * 8 + (r & 7), e = (r >> 3) & 1;
      int mul = 4 * k, add = e ? 512 : 0;
      if (k == 0 && e == 1) { mul = 1024; add = 0; }
      for (int d = 0; d < 512; d++) v[r * 512 + d] = c.v[(d * mul + add) & 2047];
    }
  }
};
struct alignas(1024) ET {
  uint16_t v[2048 * 128];
  constexpr ET() : v() {
    CosT c;
    for (int s = 0; s < 2048; s++)
      for (int j = 0; j < 64; j++) {
        const int o = (s & 31) * 8192 + (s >> 5) * 64 + j;
        v[o] = c.v[(s * j) & 2047]; v[o + 4096] = c.v[(s * j + 512) & 2047];
      }
  }
};
struct alignas(1024) DT {
  uint16_t v[64 * 64];
  constexpr DT() : v() {
    CosT c;
    for (int r = 0; r < 64; r++)
      for (int n = 0; n < 64; n++) {
        const int sg = r >> 1, s0 = (sg & ~6) | ((sg & 2) << 1) | ((sg & 4) >> 1), e = r & 1, f = n & 1;
        const int m = 64 * s0 * (n >> 1) + (e == f ? 0 : e ? -512 : 512);
        v[r * 64 + (((n >> 3) ^ (r & 7)) << 3) + (n & 7)] = c.v[m & 2047];
      }
  }
};
}

__device__ constexpr tbl::FT g_FT = tbl::FT();
__device__ constexpr tbl::ET g_ET = tbl::ET();
__device__ constexpr tbl::DT g_DT = tbl::DT();

__device__ __align__(1024) uint16_t g_X[129 * 8192];
__device__ __align__(1024) uint16_t g_T[32 * 64 * 512];
__device__ __align__(1024) uint2 g_Ts[32 * 64];
__device__ __align__(1024) uint4 g_part[128 * 3 * 1024];
__device__ __align__(16) float g_gate[16 * 128];
__device__ __align__(16) uint2 g_Wh[2 * 2048];
__device__ unsigned g_epoch[132 * 8];
__device__ unsigned g_cntX[8 * 32], g_cntT[8 * 32], g_cntP[128 * 32], g_cntW[32], g_cntH[32];
#define PROF_EV(i) do {} while (0)
#define PROF_CK(i) do {} while (0)

__device__ __forceinline__ uint32_t smem_u32(const void* p) { return (uint32_t)__cvta_generic_to_shared(p); }
__device__ __forceinline__ void mbar_init(uint32_t bar, uint32_t cnt) { asm volatile("mbarrier.init.shared::cta.b64 [%0], %1;" ::"r"(bar), "r"(cnt)); }
__device__ __forceinline__ void mbar_expect_tx(uint32_t bar, uint32_t bytes) { asm volatile("mbarrier.arrive.expect_tx.shared::cta.b64 _, [%0], %1;" ::"r"(bar), "r"(bytes) : "memory"); }
__device__ __forceinline__ void mbar_arrive(uint32_t bar) { asm volatile("mbarrier.arrive.shared::cta.b64 _, [%0];" ::"r"(bar) : "memory"); }
__device__ __forceinline__ void mbar_arrive_if(bool p, uint32_t bar) {
  asm volatile("{\n.reg .pred p;\nsetp.ne.b32 p, %1, 0;\n@p mbarrier.arrive.shared::cta.b64 _, [%0];\n}" ::"r"(bar), "r"((int)p) : "memory");
}
__device__ __forceinline__ void hint_add_if(bool p, unsigned* a) {
  asm volatile("{\n.reg .pred p;\nsetp.ne.b32 p, %1, 0;\n@p red.relaxed.gpu.global.add.u32 [%0], 1;\n}" ::"l"(a), "r"((int)p) : "memory");
}
__device__ __forceinline__ bool mbar_try(uint32_t bar, uint32_t parity) {
  uint32_t ok;
  asm volatile("{\n.reg .pred p;\nmbarrier.test_wait.parity.shared::cta.b64 p, [%1], %2;\nselp.u32 %0, 1, 0, p;\n}" : "=r"(ok) : "r"(bar), "r"(parity) : "memory");
  return ok;
}
__device__ __forceinline__ void mbar_wait(uint32_t bar, uint32_t parity) {
  asm volatile(
      "{\n.reg .pred p;\n.reg .u32 n;\nmov.u32 n, 0;\n"
      "W_LOOP:\nmbarrier.try_wait.parity.shared::cta.b64 p, [%0], %1;\n@p bra W_DONE;\n"
      "add.u32 n, n, 1;\nsetp.lt.u32 p, n, 0x40000;\n@p bra W_LOOP;\ntrap;\nW_DONE:\n}" ::"r"(bar), "r"(parity) : "memory");
}
__device__ __forceinline__ void bulk_load(uint32_t dst, const void* src, uint32_t bytes, uint32_t bar) {
  asm volatile("cp.async.bulk.shared::cluster.global.mbarrier::complete_tx::bytes [%0], [%1], %2, [%3];" ::"r"(dst), "l"(src), "r"(bytes), "r"(bar) : "memory");
}
__device__ __forceinline__ void cp16(uint32_t dst, const void* src) { asm volatile("cp.async.cg.shared.global [%0], [%1], 16;" ::"r"(dst), "l"(src) : "memory"); }
__device__ __forceinline__ void spin_guard(uint32_t t0) { if ((uint32_t)clock() - t0 > (1u << 30)) __trap(); }
__device__ __forceinline__ float tagf(float v, uint32_t tag) { return __uint_as_float((__float_as_uint(v) & ~1u) | tag); }
__device__ __forceinline__ float untag(float v) { return __uint_as_float(__float_as_uint(v) & ~1u); }
__device__ __forceinline__ void st_x2(float2* p, float a, float b) { asm volatile("st.relaxed.gpu.global.v2.f32 [%0], {%1,%2};" ::"l"(p), "f"(a), "f"(b) : "memory"); }
__device__ __forceinline__ float2 ld_x2(const float2* p) { float2 v; asm volatile("ld.relaxed.gpu.global.v2.f32 {%0,%1}, [%2];" : "=f"(v.x), "=f"(v.y) : "l"(p) : "memory"); return v; }
__device__ __forceinline__ void st_u2(uint2* p, uint32_t a, uint32_t b) { asm volatile("st.relaxed.gpu.global.v2.u32 [%0], {%1,%2};" ::"l"(p), "r"(a), "r"(b) : "memory"); }
__device__ __forceinline__ void prefetch2d(const CUtensorMap* m, int c0, int c1) { asm volatile("cp.async.bulk.prefetch.tensor.2d.L2.global [%0, {%1, %2}];" ::"l"(m), "r"(c0), "r"(c1) : "memory"); }
__device__ __forceinline__ void prefetch1d(const void* p, uint32_t bytes) { asm volatile("cp.async.bulk.prefetch.L2.global [%0], %1;" ::"l"(p), "r"(bytes) : "memory"); }
__device__ __forceinline__ uint32_t ld_x1(const void* p) { uint32_t v; asm volatile("ld.relaxed.gpu.global.u32 %0, [%1];" : "=r"(v) : "l"(p) : "memory"); return v; }
__device__ __forceinline__ uint4 ld_x4(const void* p) { uint4 v; asm volatile("ld.relaxed.gpu.global.v4.u32 {%0,%1,%2,%3}, [%4];" : "=r"(v.x), "=r"(v.y), "=r"(v.z), "=r"(v.w) : "l"(p) : "memory"); return v; }
__device__ __forceinline__ void st_x4(void* p, uint32_t a, uint32_t b, uint32_t c, uint32_t d) { asm volatile("st.relaxed.gpu.global.v4.u32 [%0], {%1,%2,%3,%4};" ::"l"(p), "r"(a), "r"(b), "r"(c), "r"(d) : "memory"); }
__device__ __forceinline__ uint32_t mapa(uint32_t a, uint32_t cta) { uint32_t r; asm volatile("mapa.shared::cluster.u32 %0, %1, %2;" : "=r"(r) : "r"(a), "r"(cta)); return r; }
__device__ __forceinline__ void stsm4t(uint32_t a, uint32_t r0, uint32_t r1, uint32_t r2, uint32_t r3) {
  asm volatile("stmatrix.sync.aligned.m8n8.x4.trans.shared.b16 [%0], {%1,%2,%3,%4};" ::"r"(a), "r"(r0), "r"(r1), "r"(r2), "r"(r3) : "memory");
}
__device__ __forceinline__ void hint_add(unsigned* p) { asm volatile("red.relaxed.gpu.global.add.u32 [%0], 1;" ::"l"(p) : "memory"); }
__device__ __forceinline__ void hint_wait(const unsigned* p, unsigned target) {
  const uint32_t t0 = (uint32_t)clock();
  while ((int)(ld_x1(p) - target) < 0) spin_guard(t0);
}
__device__ __forceinline__ void bulk_done_signal(unsigned* p) {
  asm volatile("cp.async.bulk.commit_group;\ncp.async.bulk.wait_group 0;\nfence.proxy.async.global;" ::: "memory");
  hint_add(p);
}
__device__ __forceinline__ void flag_wait(const unsigned* p, unsigned target) {
  hint_wait(p, target);
  asm volatile("fence.proxy.async.global;" ::: "memory");
}
__device__ __forceinline__ void tma2d(uint32_t dst, const CUtensorMap* m, uint32_t bar, int c0, int c1) {
  asm volatile("cp.async.bulk.tensor.2d.shared::cluster.global.mbarrier::complete_tx::bytes [%0], [%1, {%3, %4}], [%2];" ::"r"(dst), "l"(m), "r"(bar), "r"(c0), "r"(c1) : "memory");
}
__device__ __forceinline__ void tma3d(uint32_t dst, const CUtensorMap* m, uint32_t bar, int c0, int c1, int c2) {
  asm volatile("cp.async.bulk.tensor.3d.shared::cluster.global.mbarrier::complete_tx::bytes [%0], [%1, {%3, %4, %5}], [%2];" ::"r"(dst), "l"(m), "r"(bar), "r"(c0), "r"(c1), "r"(c2) : "memory");
}
__device__ __forceinline__ void tma4d(uint32_t dst, const CUtensorMap* m, uint32_t bar, int c0, int c1, int c2, int c3) {
  asm volatile("cp.async.bulk.tensor.4d.shared::cluster.global.mbarrier::complete_tx::bytes [%0], [%1, {%3, %4, %5, %6}], [%2];" ::"r"(dst), "l"(m), "r"(bar), "r"(c0), "r"(c1), "r"(c2), "r"(c3) : "memory");
}
__device__ __forceinline__ void wg_fence() { asm volatile("wgmma.fence.sync.aligned;" ::: "memory"); }
__device__ __forceinline__ void wg_commit() { asm volatile("wgmma.commit_group.sync.aligned;" ::: "memory"); }
template <int N> __device__ __forceinline__ void wg_wait() { asm volatile("wgmma.wait_group.sync.aligned %0;" ::"n"(N) : "memory"); }
template <int O, int N, int NN> __device__ __forceinline__ void fence_regs(float (&d)[NN]) {
#pragma unroll
  for (int i = 0; i < N; i++) asm volatile("" : "+f"(d[O + i])::"memory");
}
__device__ __forceinline__ uint32_t pack_bf16(float lo, float hi) {
  uint32_t r; asm("cvt.rn.bf16x2.f32 %0, %1, %2;" : "=r"(r) : "f"(hi), "f"(lo)); return r;
}
__device__ __forceinline__ uint32_t pack_pin(float lo, float hi) {
  uint32_t r; asm volatile("cvt.rn.bf16x2.f32 %0, %1, %2;" : "=r"(r) : "f"(hi), "f"(lo) : "memory"); return r;
}
__device__ __forceinline__ float bf_lo(uint32_t u) { return __uint_as_float(u << 16); }
__device__ __forceinline__ float bf_hi(uint32_t u) { return __uint_as_float(u & 0xffff0000u); }

__device__ __forceinline__ uint64_t d128(uint32_t lo) { uint64_t d; asm("mov.b64 %0, {%1, 0x40000040};" : "=l"(d) : "r"(lo)); return d; }
__device__ __forceinline__ uint64_t d64(uint32_t lo) { uint64_t d; asm("mov.b64 %0, {%1, 0x80000020};" : "=l"(d) : "r"(lo)); return d; }
template<int O,int TB,int ACC,int NN> __device__ __forceinline__ void mma_ss64(float (&d)[NN], uint64_t da, uint64_t db, int sd = 0){
  if constexpr (ACC == 1) asm volatile("wgmma.mma_async.sync.aligned.m64n64k16.f32.bf16.bf16 {%0,%1,%2,%3,%4,%5,%6,%7,%8,%9,%10,%11,%12,%13,%14,%15,%16,%17,%18,%19,%20,%21,%22,%23,%24,%25,%26,%27,%28,%29,%30,%31}, %32, %33, 1, 1, 1, %35, %34;"
   : "+f"(d[O+0]), "+f"(d[O+1]), "+f"(d[O+2]), "+f"(d[O+3]), "+f"(d[O+4]), "+f"(d[O+5]), "+f"(d[O+6]), "+f"(d[O+7]), "+f"(d[O+8]), "+f"(d[O+9]), "+f"(d[O+10]), "+f"(d[O+11]), "+f"(d[O+12]), "+f"(d[O+13]), "+f"(d[O+14]), "+f"(d[O+15]), "+f"(d[O+16]), "+f"(d[O+17]), "+f"(d[O+18]), "+f"(d[O+19]), "+f"(d[O+20]), "+f"(d[O+21]), "+f"(d[O+22]), "+f"(d[O+23]), "+f"(d[O+24]), "+f"(d[O+25]), "+f"(d[O+26]), "+f"(d[O+27]), "+f"(d[O+28]), "+f"(d[O+29]), "+f"(d[O+30]), "+f"(d[O+31])
   : "l"(da), "l"(db), "n"(TB & 1), "n"(TB >> 1));
  else if constexpr (ACC == 0) asm volatile("wgmma.mma_async.sync.aligned.m64n64k16.f32.bf16.bf16 {%0,%1,%2,%3,%4,%5,%6,%7,%8,%9,%10,%11,%12,%13,%14,%15,%16,%17,%18,%19,%20,%21,%22,%23,%24,%25,%26,%27,%28,%29,%30,%31}, %32, %33, 0, 1, 1, %35, %34;"
   : "=f"(d[O+0]), "=f"(d[O+1]), "=f"(d[O+2]), "=f"(d[O+3]), "=f"(d[O+4]), "=f"(d[O+5]), "=f"(d[O+6]), "=f"(d[O+7]), "=f"(d[O+8]), "=f"(d[O+9]), "=f"(d[O+10]), "=f"(d[O+11]), "=f"(d[O+12]), "=f"(d[O+13]), "=f"(d[O+14]), "=f"(d[O+15]), "=f"(d[O+16]), "=f"(d[O+17]), "=f"(d[O+18]), "=f"(d[O+19]), "=f"(d[O+20]), "=f"(d[O+21]), "=f"(d[O+22]), "=f"(d[O+23]), "=f"(d[O+24]), "=f"(d[O+25]), "=f"(d[O+26]), "=f"(d[O+27]), "=f"(d[O+28]), "=f"(d[O+29]), "=f"(d[O+30]), "=f"(d[O+31])
   : "l"(da), "l"(db), "n"(TB & 1), "n"(TB >> 1));
  else asm volatile("{\n.reg .pred p;\nsetp.ne.b32 p, %36, 0;\nwgmma.mma_async.sync.aligned.m64n64k16.f32.bf16.bf16 {%0,%1,%2,%3,%4,%5,%6,%7,%8,%9,%10,%11,%12,%13,%14,%15,%16,%17,%18,%19,%20,%21,%22,%23,%24,%25,%26,%27,%28,%29,%30,%31}, %32, %33, p, 1, 1, %35, %34;\n}"
   : "+f"(d[O+0]), "+f"(d[O+1]), "+f"(d[O+2]), "+f"(d[O+3]), "+f"(d[O+4]), "+f"(d[O+5]), "+f"(d[O+6]), "+f"(d[O+7]), "+f"(d[O+8]), "+f"(d[O+9]), "+f"(d[O+10]), "+f"(d[O+11]), "+f"(d[O+12]), "+f"(d[O+13]), "+f"(d[O+14]), "+f"(d[O+15]), "+f"(d[O+16]), "+f"(d[O+17]), "+f"(d[O+18]), "+f"(d[O+19]), "+f"(d[O+20]), "+f"(d[O+21]), "+f"(d[O+22]), "+f"(d[O+23]), "+f"(d[O+24]), "+f"(d[O+25]), "+f"(d[O+26]), "+f"(d[O+27]), "+f"(d[O+28]), "+f"(d[O+29]), "+f"(d[O+30]), "+f"(d[O+31])
   : "l"(da), "l"(db), "n"(TB & 1), "n"(TB >> 1), "r"(sd));
}
template<int O,int TB,int ACC,int NN> __device__ __forceinline__ void mma_rs64(float (&d)[NN], uint32_t a0, uint32_t a1, uint32_t a2, uint32_t a3, uint64_t db, int sd = 0){
  if constexpr (ACC == 1) asm volatile("wgmma.mma_async.sync.aligned.m64n64k16.f32.bf16.bf16 {%0,%1,%2,%3,%4,%5,%6,%7,%8,%9,%10,%11,%12,%13,%14,%15,%16,%17,%18,%19,%20,%21,%22,%23,%24,%25,%26,%27,%28,%29,%30,%31}, {%32,%33,%34,%35}, %36, 1, 1, 1, %37;"
   : "+f"(d[O+0]), "+f"(d[O+1]), "+f"(d[O+2]), "+f"(d[O+3]), "+f"(d[O+4]), "+f"(d[O+5]), "+f"(d[O+6]), "+f"(d[O+7]), "+f"(d[O+8]), "+f"(d[O+9]), "+f"(d[O+10]), "+f"(d[O+11]), "+f"(d[O+12]), "+f"(d[O+13]), "+f"(d[O+14]), "+f"(d[O+15]), "+f"(d[O+16]), "+f"(d[O+17]), "+f"(d[O+18]), "+f"(d[O+19]), "+f"(d[O+20]), "+f"(d[O+21]), "+f"(d[O+22]), "+f"(d[O+23]), "+f"(d[O+24]), "+f"(d[O+25]), "+f"(d[O+26]), "+f"(d[O+27]), "+f"(d[O+28]), "+f"(d[O+29]), "+f"(d[O+30]), "+f"(d[O+31])
   : "r"(a0), "r"(a1), "r"(a2), "r"(a3), "l"(db), "n"(TB));
  else if constexpr (ACC == 0) asm volatile("wgmma.mma_async.sync.aligned.m64n64k16.f32.bf16.bf16 {%0,%1,%2,%3,%4,%5,%6,%7,%8,%9,%10,%11,%12,%13,%14,%15,%16,%17,%18,%19,%20,%21,%22,%23,%24,%25,%26,%27,%28,%29,%30,%31}, {%32,%33,%34,%35}, %36, 0, 1, 1, %37;"
   : "=f"(d[O+0]), "=f"(d[O+1]), "=f"(d[O+2]), "=f"(d[O+3]), "=f"(d[O+4]), "=f"(d[O+5]), "=f"(d[O+6]), "=f"(d[O+7]), "=f"(d[O+8]), "=f"(d[O+9]), "=f"(d[O+10]), "=f"(d[O+11]), "=f"(d[O+12]), "=f"(d[O+13]), "=f"(d[O+14]), "=f"(d[O+15]), "=f"(d[O+16]), "=f"(d[O+17]), "=f"(d[O+18]), "=f"(d[O+19]), "=f"(d[O+20]), "=f"(d[O+21]), "=f"(d[O+22]), "=f"(d[O+23]), "=f"(d[O+24]), "=f"(d[O+25]), "=f"(d[O+26]), "=f"(d[O+27]), "=f"(d[O+28]), "=f"(d[O+29]), "=f"(d[O+30]), "=f"(d[O+31])
   : "r"(a0), "r"(a1), "r"(a2), "r"(a3), "l"(db), "n"(TB));
  else asm volatile("{\n.reg .pred p;\nsetp.ne.b32 p, %38, 0;\nwgmma.mma_async.sync.aligned.m64n64k16.f32.bf16.bf16 {%0,%1,%2,%3,%4,%5,%6,%7,%8,%9,%10,%11,%12,%13,%14,%15,%16,%17,%18,%19,%20,%21,%22,%23,%24,%25,%26,%27,%28,%29,%30,%31}, {%32,%33,%34,%35}, %36, p, 1, 1, %37;\n}"
   : "+f"(d[O+0]), "+f"(d[O+1]), "+f"(d[O+2]), "+f"(d[O+3]), "+f"(d[O+4]), "+f"(d[O+5]), "+f"(d[O+6]), "+f"(d[O+7]), "+f"(d[O+8]), "+f"(d[O+9]), "+f"(d[O+10]), "+f"(d[O+11]), "+f"(d[O+12]), "+f"(d[O+13]), "+f"(d[O+14]), "+f"(d[O+15]), "+f"(d[O+16]), "+f"(d[O+17]), "+f"(d[O+18]), "+f"(d[O+19]), "+f"(d[O+20]), "+f"(d[O+21]), "+f"(d[O+22]), "+f"(d[O+23]), "+f"(d[O+24]), "+f"(d[O+25]), "+f"(d[O+26]), "+f"(d[O+27]), "+f"(d[O+28]), "+f"(d[O+29]), "+f"(d[O+30]), "+f"(d[O+31])
   : "r"(a0), "r"(a1), "r"(a2), "r"(a3), "l"(db), "n"(TB), "r"(sd));
}
template<int O,int TB,int ACC,int NN> __device__ __forceinline__ void mma_ss128(float (&d)[NN], uint64_t da, uint64_t db, int sd = 0){
  if constexpr (ACC == 1) asm volatile("wgmma.mma_async.sync.aligned.m64n128k16.f32.bf16.bf16 {%0,%1,%2,%3,%4,%5,%6,%7,%8,%9,%10,%11,%12,%13,%14,%15,%16,%17,%18,%19,%20,%21,%22,%23,%24,%25,%26,%27,%28,%29,%30,%31,%32,%33,%34,%35,%36,%37,%38,%39,%40,%41,%42,%43,%44,%45,%46,%47,%48,%49,%50,%51,%52,%53,%54,%55,%56,%57,%58,%59,%60,%61,%62,%63}, %64, %65, 1, 1, 1, %67, %66;"
   : "+f"(d[O+0]), "+f"(d[O+1]), "+f"(d[O+2]), "+f"(d[O+3]), "+f"(d[O+4]), "+f"(d[O+5]), "+f"(d[O+6]), "+f"(d[O+7]), "+f"(d[O+8]), "+f"(d[O+9]), "+f"(d[O+10]), "+f"(d[O+11]), "+f"(d[O+12]), "+f"(d[O+13]), "+f"(d[O+14]), "+f"(d[O+15]), "+f"(d[O+16]), "+f"(d[O+17]), "+f"(d[O+18]), "+f"(d[O+19]), "+f"(d[O+20]), "+f"(d[O+21]), "+f"(d[O+22]), "+f"(d[O+23]), "+f"(d[O+24]), "+f"(d[O+25]), "+f"(d[O+26]), "+f"(d[O+27]), "+f"(d[O+28]), "+f"(d[O+29]), "+f"(d[O+30]), "+f"(d[O+31]), "+f"(d[O+32]), "+f"(d[O+33]), "+f"(d[O+34]), "+f"(d[O+35]), "+f"(d[O+36]), "+f"(d[O+37]), "+f"(d[O+38]), "+f"(d[O+39]), "+f"(d[O+40]), "+f"(d[O+41]), "+f"(d[O+42]), "+f"(d[O+43]), "+f"(d[O+44]), "+f"(d[O+45]), "+f"(d[O+46]), "+f"(d[O+47]), "+f"(d[O+48]), "+f"(d[O+49]), "+f"(d[O+50]), "+f"(d[O+51]), "+f"(d[O+52]), "+f"(d[O+53]), "+f"(d[O+54]), "+f"(d[O+55]), "+f"(d[O+56]), "+f"(d[O+57]), "+f"(d[O+58]), "+f"(d[O+59]), "+f"(d[O+60]), "+f"(d[O+61]), "+f"(d[O+62]), "+f"(d[O+63])
   : "l"(da), "l"(db), "n"(TB & 1), "n"(TB >> 1));
  else if constexpr (ACC == 0) asm volatile("wgmma.mma_async.sync.aligned.m64n128k16.f32.bf16.bf16 {%0,%1,%2,%3,%4,%5,%6,%7,%8,%9,%10,%11,%12,%13,%14,%15,%16,%17,%18,%19,%20,%21,%22,%23,%24,%25,%26,%27,%28,%29,%30,%31,%32,%33,%34,%35,%36,%37,%38,%39,%40,%41,%42,%43,%44,%45,%46,%47,%48,%49,%50,%51,%52,%53,%54,%55,%56,%57,%58,%59,%60,%61,%62,%63}, %64, %65, 0, 1, 1, %67, %66;"
   : "=f"(d[O+0]), "=f"(d[O+1]), "=f"(d[O+2]), "=f"(d[O+3]), "=f"(d[O+4]), "=f"(d[O+5]), "=f"(d[O+6]), "=f"(d[O+7]), "=f"(d[O+8]), "=f"(d[O+9]), "=f"(d[O+10]), "=f"(d[O+11]), "=f"(d[O+12]), "=f"(d[O+13]), "=f"(d[O+14]), "=f"(d[O+15]), "=f"(d[O+16]), "=f"(d[O+17]), "=f"(d[O+18]), "=f"(d[O+19]), "=f"(d[O+20]), "=f"(d[O+21]), "=f"(d[O+22]), "=f"(d[O+23]), "=f"(d[O+24]), "=f"(d[O+25]), "=f"(d[O+26]), "=f"(d[O+27]), "=f"(d[O+28]), "=f"(d[O+29]), "=f"(d[O+30]), "=f"(d[O+31]), "=f"(d[O+32]), "=f"(d[O+33]), "=f"(d[O+34]), "=f"(d[O+35]), "=f"(d[O+36]), "=f"(d[O+37]), "=f"(d[O+38]), "=f"(d[O+39]), "=f"(d[O+40]), "=f"(d[O+41]), "=f"(d[O+42]), "=f"(d[O+43]), "=f"(d[O+44]), "=f"(d[O+45]), "=f"(d[O+46]), "=f"(d[O+47]), "=f"(d[O+48]), "=f"(d[O+49]), "=f"(d[O+50]), "=f"(d[O+51]), "=f"(d[O+52]), "=f"(d[O+53]), "=f"(d[O+54]), "=f"(d[O+55]), "=f"(d[O+56]), "=f"(d[O+57]), "=f"(d[O+58]), "=f"(d[O+59]), "=f"(d[O+60]), "=f"(d[O+61]), "=f"(d[O+62]), "=f"(d[O+63])
   : "l"(da), "l"(db), "n"(TB & 1), "n"(TB >> 1));
  else asm volatile("{\n.reg .pred p;\nsetp.ne.b32 p, %68, 0;\nwgmma.mma_async.sync.aligned.m64n128k16.f32.bf16.bf16 {%0,%1,%2,%3,%4,%5,%6,%7,%8,%9,%10,%11,%12,%13,%14,%15,%16,%17,%18,%19,%20,%21,%22,%23,%24,%25,%26,%27,%28,%29,%30,%31,%32,%33,%34,%35,%36,%37,%38,%39,%40,%41,%42,%43,%44,%45,%46,%47,%48,%49,%50,%51,%52,%53,%54,%55,%56,%57,%58,%59,%60,%61,%62,%63}, %64, %65, p, 1, 1, %67, %66;\n}"
   : "+f"(d[O+0]), "+f"(d[O+1]), "+f"(d[O+2]), "+f"(d[O+3]), "+f"(d[O+4]), "+f"(d[O+5]), "+f"(d[O+6]), "+f"(d[O+7]), "+f"(d[O+8]), "+f"(d[O+9]), "+f"(d[O+10]), "+f"(d[O+11]), "+f"(d[O+12]), "+f"(d[O+13]), "+f"(d[O+14]), "+f"(d[O+15]), "+f"(d[O+16]), "+f"(d[O+17]), "+f"(d[O+18]), "+f"(d[O+19]), "+f"(d[O+20]), "+f"(d[O+21]), "+f"(d[O+22]), "+f"(d[O+23]), "+f"(d[O+24]), "+f"(d[O+25]), "+f"(d[O+26]), "+f"(d[O+27]), "+f"(d[O+28]), "+f"(d[O+29]), "+f"(d[O+30]), "+f"(d[O+31]), "+f"(d[O+32]), "+f"(d[O+33]), "+f"(d[O+34]), "+f"(d[O+35]), "+f"(d[O+36]), "+f"(d[O+37]), "+f"(d[O+38]), "+f"(d[O+39]), "+f"(d[O+40]), "+f"(d[O+41]), "+f"(d[O+42]), "+f"(d[O+43]), "+f"(d[O+44]), "+f"(d[O+45]), "+f"(d[O+46]), "+f"(d[O+47]), "+f"(d[O+48]), "+f"(d[O+49]), "+f"(d[O+50]), "+f"(d[O+51]), "+f"(d[O+52]), "+f"(d[O+53]), "+f"(d[O+54]), "+f"(d[O+55]), "+f"(d[O+56]), "+f"(d[O+57]), "+f"(d[O+58]), "+f"(d[O+59]), "+f"(d[O+60]), "+f"(d[O+61]), "+f"(d[O+62]), "+f"(d[O+63])
   : "l"(da), "l"(db), "n"(TB & 1), "n"(TB >> 1), "r"(sd));
}
template<int O,int TB,int ACC,int NN> __device__ __forceinline__ void mma_rs128(float (&d)[NN], uint32_t a0, uint32_t a1, uint32_t a2, uint32_t a3, uint64_t db, int sd = 0){
  if constexpr (ACC == 1) asm volatile("wgmma.mma_async.sync.aligned.m64n128k16.f32.bf16.bf16 {%0,%1,%2,%3,%4,%5,%6,%7,%8,%9,%10,%11,%12,%13,%14,%15,%16,%17,%18,%19,%20,%21,%22,%23,%24,%25,%26,%27,%28,%29,%30,%31,%32,%33,%34,%35,%36,%37,%38,%39,%40,%41,%42,%43,%44,%45,%46,%47,%48,%49,%50,%51,%52,%53,%54,%55,%56,%57,%58,%59,%60,%61,%62,%63}, {%64,%65,%66,%67}, %68, 1, 1, 1, %69;"
   : "+f"(d[O+0]), "+f"(d[O+1]), "+f"(d[O+2]), "+f"(d[O+3]), "+f"(d[O+4]), "+f"(d[O+5]), "+f"(d[O+6]), "+f"(d[O+7]), "+f"(d[O+8]), "+f"(d[O+9]), "+f"(d[O+10]), "+f"(d[O+11]), "+f"(d[O+12]), "+f"(d[O+13]), "+f"(d[O+14]), "+f"(d[O+15]), "+f"(d[O+16]), "+f"(d[O+17]), "+f"(d[O+18]), "+f"(d[O+19]), "+f"(d[O+20]), "+f"(d[O+21]), "+f"(d[O+22]), "+f"(d[O+23]), "+f"(d[O+24]), "+f"(d[O+25]), "+f"(d[O+26]), "+f"(d[O+27]), "+f"(d[O+28]), "+f"(d[O+29]), "+f"(d[O+30]), "+f"(d[O+31]), "+f"(d[O+32]), "+f"(d[O+33]), "+f"(d[O+34]), "+f"(d[O+35]), "+f"(d[O+36]), "+f"(d[O+37]), "+f"(d[O+38]), "+f"(d[O+39]), "+f"(d[O+40]), "+f"(d[O+41]), "+f"(d[O+42]), "+f"(d[O+43]), "+f"(d[O+44]), "+f"(d[O+45]), "+f"(d[O+46]), "+f"(d[O+47]), "+f"(d[O+48]), "+f"(d[O+49]), "+f"(d[O+50]), "+f"(d[O+51]), "+f"(d[O+52]), "+f"(d[O+53]), "+f"(d[O+54]), "+f"(d[O+55]), "+f"(d[O+56]), "+f"(d[O+57]), "+f"(d[O+58]), "+f"(d[O+59]), "+f"(d[O+60]), "+f"(d[O+61]), "+f"(d[O+62]), "+f"(d[O+63])
   : "r"(a0), "r"(a1), "r"(a2), "r"(a3), "l"(db), "n"(TB));
  else if constexpr (ACC == 0) asm volatile("wgmma.mma_async.sync.aligned.m64n128k16.f32.bf16.bf16 {%0,%1,%2,%3,%4,%5,%6,%7,%8,%9,%10,%11,%12,%13,%14,%15,%16,%17,%18,%19,%20,%21,%22,%23,%24,%25,%26,%27,%28,%29,%30,%31,%32,%33,%34,%35,%36,%37,%38,%39,%40,%41,%42,%43,%44,%45,%46,%47,%48,%49,%50,%51,%52,%53,%54,%55,%56,%57,%58,%59,%60,%61,%62,%63}, {%64,%65,%66,%67}, %68, 0, 1, 1, %69;"
   : "=f"(d[O+0]), "=f"(d[O+1]), "=f"(d[O+2]), "=f"(d[O+3]), "=f"(d[O+4]), "=f"(d[O+5]), "=f"(d[O+6]), "=f"(d[O+7]), "=f"(d[O+8]), "=f"(d[O+9]), "=f"(d[O+10]), "=f"(d[O+11]), "=f"(d[O+12]), "=f"(d[O+13]), "=f"(d[O+14]), "=f"(d[O+15]), "=f"(d[O+16]), "=f"(d[O+17]), "=f"(d[O+18]), "=f"(d[O+19]), "=f"(d[O+20]), "=f"(d[O+21]), "=f"(d[O+22]), "=f"(d[O+23]), "=f"(d[O+24]), "=f"(d[O+25]), "=f"(d[O+26]), "=f"(d[O+27]), "=f"(d[O+28]), "=f"(d[O+29]), "=f"(d[O+30]), "=f"(d[O+31]), "=f"(d[O+32]), "=f"(d[O+33]), "=f"(d[O+34]), "=f"(d[O+35]), "=f"(d[O+36]), "=f"(d[O+37]), "=f"(d[O+38]), "=f"(d[O+39]), "=f"(d[O+40]), "=f"(d[O+41]), "=f"(d[O+42]), "=f"(d[O+43]), "=f"(d[O+44]), "=f"(d[O+45]), "=f"(d[O+46]), "=f"(d[O+47]), "=f"(d[O+48]), "=f"(d[O+49]), "=f"(d[O+50]), "=f"(d[O+51]), "=f"(d[O+52]), "=f"(d[O+53]), "=f"(d[O+54]), "=f"(d[O+55]), "=f"(d[O+56]), "=f"(d[O+57]), "=f"(d[O+58]), "=f"(d[O+59]), "=f"(d[O+60]), "=f"(d[O+61]), "=f"(d[O+62]), "=f"(d[O+63])
   : "r"(a0), "r"(a1), "r"(a2), "r"(a3), "l"(db), "n"(TB));
  else asm volatile("{\n.reg .pred p;\nsetp.ne.b32 p, %70, 0;\nwgmma.mma_async.sync.aligned.m64n128k16.f32.bf16.bf16 {%0,%1,%2,%3,%4,%5,%6,%7,%8,%9,%10,%11,%12,%13,%14,%15,%16,%17,%18,%19,%20,%21,%22,%23,%24,%25,%26,%27,%28,%29,%30,%31,%32,%33,%34,%35,%36,%37,%38,%39,%40,%41,%42,%43,%44,%45,%46,%47,%48,%49,%50,%51,%52,%53,%54,%55,%56,%57,%58,%59,%60,%61,%62,%63}, {%64,%65,%66,%67}, %68, p, 1, 1, %69;\n}"
   : "+f"(d[O+0]), "+f"(d[O+1]), "+f"(d[O+2]), "+f"(d[O+3]), "+f"(d[O+4]), "+f"(d[O+5]), "+f"(d[O+6]), "+f"(d[O+7]), "+f"(d[O+8]), "+f"(d[O+9]), "+f"(d[O+10]), "+f"(d[O+11]), "+f"(d[O+12]), "+f"(d[O+13]), "+f"(d[O+14]), "+f"(d[O+15]), "+f"(d[O+16]), "+f"(d[O+17]), "+f"(d[O+18]), "+f"(d[O+19]), "+f"(d[O+20]), "+f"(d[O+21]), "+f"(d[O+22]), "+f"(d[O+23]), "+f"(d[O+24]), "+f"(d[O+25]), "+f"(d[O+26]), "+f"(d[O+27]), "+f"(d[O+28]), "+f"(d[O+29]), "+f"(d[O+30]), "+f"(d[O+31]), "+f"(d[O+32]), "+f"(d[O+33]), "+f"(d[O+34]), "+f"(d[O+35]), "+f"(d[O+36]), "+f"(d[O+37]), "+f"(d[O+38]), "+f"(d[O+39]), "+f"(d[O+40]), "+f"(d[O+41]), "+f"(d[O+42]), "+f"(d[O+43]), "+f"(d[O+44]), "+f"(d[O+45]), "+f"(d[O+46]), "+f"(d[O+47]), "+f"(d[O+48]), "+f"(d[O+49]), "+f"(d[O+50]), "+f"(d[O+51]), "+f"(d[O+52]), "+f"(d[O+53]), "+f"(d[O+54]), "+f"(d[O+55]), "+f"(d[O+56]), "+f"(d[O+57]), "+f"(d[O+58]), "+f"(d[O+59]), "+f"(d[O+60]), "+f"(d[O+61]), "+f"(d[O+62]), "+f"(d[O+63])
   : "r"(a0), "r"(a1), "r"(a2), "r"(a3), "l"(db), "n"(TB), "r"(sd));
}

#define NEARLY 0
#define XAHEAD 3
#define HM 2
#define WBATCH 1
#define SPACE 0
#define WPF 0
#define WAFTER 7
#define WPACE 0
#define GATE_AT 4
#define TPACE 40
#define PFMODE 0
#define MAPMODE 0
template <int V> struct IC { static constexpr int value = V; };
struct Maps { CUtensorMap x, ft, g64, u64, e, wr, wi, xs, ts, t, g32, u32, d224; };

constexpr int NCTA = 130;
constexpr int U = 16384;
constexpr int TB = 36864;
constexpr int OFF_RING = 8 * U, OFF_Z = 9 * U, OFF_XB = 12 * U, OFF_T = 13 * U, OFF_D = OFF_T;
constexpr int OFF_BAR = 14 * U, OFF_SP = OFF_BAR + 512, OFF_G = OFF_SP + 1024 + 128;
constexpr int SMEM_BYTES = OFF_G + 512;
constexpr int B_FX = 0, B_FA = 8, B_FT = 12, B_Z = 16, B_W = 20, B_HX = 21, B_TL = 22, B_HP = 23, B_WR = 26, B_E0 = 30;
constexpr int B_EA = 31, B_ET = 35, B_PZ = 39, B_RDY = 41, B_FE = 42;
constexpr int B_T = 46, B_XS = 47, B_G = 49, NBAR = 50;
__host__ __device__ constexpr int rslot(int n) { return n & 3; }
__host__ __device__ constexpr int rpar(int n) { return (n >> 2) & 1; }

__global__ void __cluster_dims__(2, 1, 1) __launch_bounds__(512, 1)
fused_kernel(const __grid_constant__ Maps maps, const __nv_bfloat16* __restrict__ x, const __nv_bfloat16* __restrict__ w_r,
             const __nv_bfloat16* __restrict__ w_i, const __nv_bfloat16* __restrict__ gate_w, __nv_bfloat16* __restrict__ out) {
  extern __shared__ __align__(1024) uint8_t smem[];
  const uint32_t sb = smem_u32(smem);
  const uint32_t bars = sb + OFF_BAR;
  const int tid = threadIdx.x, lane = tid & 31;
  const int warp = __shfl_sync(0xffffffffu, tid >> 5, 0);
  const bool helper = blockIdx.x >= 128;
  const int cl = (blockIdx.x >> 1) & 63, rank = blockIdx.x & 1;
  const int q4 = cl & 3, rb = cl >> 2;
  const int j = 2 * q4 + rank;
  const int f_full = 448 * q4 + (rank ? 256 : 0);
  const int f_half = 448 * q4 + (rank ? 224 : 192);
  const int kg = 2 * j + (rb >> 3), tn = rb & 7;

  if (tid == 64) { PROF_EV(0); PROF_CK(40); }
  if (warp < 8) {
    asm volatile("barrier.cluster.arrive.relaxed.aligned;" ::: "memory");
    asm volatile("setmaxnreg.inc.sync.aligned.u32 192;");
    if (!helper) {
      const int wg = warp >> 2, w = warp & 3, g = lane >> 2;
      const bool elect = (tid & 127) == 0;
      float cX[32], cA[64], cB[64], cC[64], ci[64], ct[64];
      const int zero = blockIdx.x >> 16;
      uint32_t h[56], yf[16];
      const uint32_t d0 = (sb & 0x3FFFF) >> 4;
      const uint32_t dK = d0 | (1u << 16), dN = d0 | (512u << 16);
      const uint32_t dX = dK + wg * 512;
      constexpr uint32_t RING = OFF_RING >> 4;
      auto waitA = [&](int n) { mbar_wait(bars + 8 * (B_FA + rslot(n)), rpar(n)); };
      auto freeA = [&](int n) { mbar_arrive_if(elect, bars + 8 * (B_EA + rslot(n))); };
      auto nop = [] {};

      asm volatile("bar.sync 0, 384;" ::: "memory");
#pragma unroll 1
      for (int i = 0; i < 4; i++) {
        const uint64_t dx = d128(dX + i * 2048), df = d128(dK + (OFF_XB >> 4) + (i & 1) * 1024);
        mbar_wait(bars + 8 * (B_FX + 2 * i), 0);
        wg_fence();
        mma_ss64<0, 0, 2>(cX, df, dx, i);
        mma_ss64<0, 0, 1>(cX, df + 2, dx + 2);
        wg_commit(); wg_wait<1>();
        mbar_arrive_if(elect && i, bars + 8 * (B_EA + rslot(i - 1)));
        mma_ss64<0, 0, 1>(cX, df + 4, dx + 4);
        mma_ss64<0, 0, 1>(cX, df + 6, dx + 6);
        if (i == 0 && tid == 0) PROF_EV(1);
        mbar_wait(bars + 8 * (B_FX + 2 * i + 1), 0);
        wg_fence();
#pragma unroll
        for (int k = 0; k < 4; k++) mma_ss64<0, 0, 1>(cX, df + (512 + k * 2), dx + (1024 + k * 2));
        wg_commit();
        waitA(i);
        wg_fence();
        const uint64_t da = d128(dX + i * 1024), db = d128(dN + RING + i * 1024);
        mma_ss128<0, 1, 2>(cA, da, db, i);
        wg_commit(); wg_wait<1>();
        mbar_arrive_if(elect, bars + 8 * (B_FE + i));
#pragma unroll
        for (int k = 1; k < 4; k++) mma_ss128<0, 1, 1>(cA, da + k * 2, db + k * 128);
        wg_commit();
      }
      fence_regs<0, 32>(cX);
#pragma unroll
      for (int e = 0; e < 16; e++) yf[e] = pack_pin(cX[2 * e], cX[2 * e + 1]);
      if (tid == 0) PROF_EV(2);
      {
        waitA(4); mbar_wait(bars + 8 * B_E0, 0);
        const uint64_t de = d128(dN + (wg ? RING : OFF_XB >> 4));
        wg_fence();
        mma_rs128<0, 1, 0>(cB, yf[0], yf[1], yf[2], yf[3], de);
        wg_commit();
        wg_wait<1>();
        freeA(3);
#pragma unroll
        for (int k = 1; k < 4; k++) mma_rs128<0, 1, 1>(cB, yf[4 * k], yf[4 * k + 1], yf[4 * k + 2], yf[4 * k + 3], de + k * 128);
        wg_commit();
      }
      bool rel = false;
      auto acquire = [&](int n) {
        rel = elect;
        if (!mbar_try(bars + 8 * (B_FA + rslot(n)), rpar(n))) { wg_wait<0>(); freeA(n - 1); rel = false; waitA(n); }
      };
      auto freeP = [&](int n) { mbar_arrive_if(rel, bars + 8 * (B_EA + rslot(n - 1))); };
      auto ffn_step = [&](auto first, auto split, float (&acc)[64], int n, int kb, auto done, auto work) {
        constexpr int SPLIT = decltype(split)::value;
        acquire(n);
        wg_fence();
        const uint64_t dx = d128(dX + kb * 1024), db = d128(dN + RING + rslot(n) * 1024);
        mma_ss128<0, 1, decltype(first)::value>(acc, dx, db, zero);
#pragma unroll
        for (int k = 1; k < SPLIT; k++) mma_ss128<0, 1, 1>(acc, dx + k * 2, db + k * 128);
        wg_commit();
        work();
        wg_wait<1>();
        freeP(n);
        done();
        if (SPLIT < 4) {
          wg_fence();
#pragma unroll
          for (int k = SPLIT; k < 4; k++) mma_ss128<0, 1, 1>(acc, dx + k * 2, db + k * 128);
          wg_commit();
        }
      };
      {
        const int s0 = 2 * rb + wg, kr = 2 * ((s0 & 1) | ((s0 & 4) >> 1));
        const int m = lane >> 3, r = lane & 7;
        const uint32_t a0 = sb + OFF_XB + wg * 8192 + (((w >> 1) * 8 + (m >> 1)) * 2 + (w & 1)) * 256 + (m & 1) * 128 + ((r ^ (kr + (m & 1))) << 4);
        ffn_step(IC<1>(), IC<4>(), cA, 5, 4, [&] { fence_regs<0, 64>(cB); }, nop);
        asm volatile("bar.sync 5, 256;" ::: "memory");
#pragma unroll
        for (int i = 0; i < 4; i++)
          stsm4t(a0 + i * 1024, pack_bf16(cB[8 * i] - cB[34 + 8 * i], cB[8 * i + 1] - cB[35 + 8 * i]),
                 pack_bf16(cB[32 + 8 * i] + cB[8 * i + 2], cB[33 + 8 * i] + cB[8 * i + 3]),
                 pack_bf16(cB[8 * i + 4] - cB[38 + 8 * i], cB[8 * i + 5] - cB[39 + 8 * i]),
                 pack_bf16(cB[36 + 8 * i] + cB[8 * i + 6], cB[37 + 8 * i] + cB[8 * i + 7]));
        if (j == 0 && w == 0) {
          const uint32_t a1 = r ? sb + OFF_SP + 1024 : sb + OFF_SP + wg * 512 + (m & 1) * 256 + (m >> 1) * 128;
#pragma unroll
          for (int n = 0; n < 8; n++)
            asm volatile("stmatrix.sync.aligned.m8n8.x4.shared.b16 [%0], {%1,%2,%3,%4};" ::"r"(a1 + ((n ^ (kr + (m >> 1))) << 4)),
                         "r"(pack_bf16(cB[4 * n], cB[4 * n + 1])), "r"(pack_bf16(cB[4 * n + 2], cB[4 * n + 3])),
                         "r"(pack_bf16(cB[32 + 4 * n], cB[33 + 4 * n])), "r"(pack_bf16(cB[34 + 4 * n], cB[35 + 4 * n])) : "memory");
        }
        ffn_step(IC<1>(), IC<2>(), cA, 6, 5, nop, [&] {
          asm volatile("fence.proxy.async.shared::cta;" ::: "memory");
          __syncwarp();
          mbar_arrive_if(lane == 0, bars + 8 * (B_XS + wg));
          if (tid == 0) PROF_EV(3);
        });
      }
#pragma unroll 1
      for (int kb = 6; kb < 8; kb++) ffn_step(IC<1>(), IC<1>(), cA, 1 + kb, kb, nop, nop);
      ffn_step(IC<2>(), IC<1>(), cB, 9, 0, [&] { fence_regs<0, 64>(cA); }, nop);
#pragma unroll 1
      for (int kb = 1; kb < 6; kb++) ffn_step(IC<1>(), IC<1>(), cB, 9 + kb, kb, nop, nop);
      mbar_wait(bars + 8 * B_G, 0);
      const uint32_t gb0 = *(const uint32_t*)(smem + OFF_G + (wg * 64 + w * 16 + g) * 4), gb1 = *(const uint32_t*)(smem + OFF_G + (wg * 64 + w * 16 + g + 8) * 4);
      const uint32_t tag = gb0 & 1;
      const float g0 = __uint_as_float(gb0 & ~1u), g1 = __uint_as_float(gb1 & ~1u);
      const float o0 = 1.0f - g0, o1 = 1.0f - g1;
      auto glu = [&](auto& acc, int half, int ho, int i0, int i1) {
#pragma unroll
        for (int i = i0; i < i1; i++) {
          const float o = (i & 1) ? o1 : o0;
          h[ho + i] = pack_pin(fmaxf(acc[2 * i], 0.f) * acc[half + 2 * i] * o, fmaxf(acc[2 * i + 1], 0.f) * acc[half + 1 + 2 * i] * o);
        }
      };
      ffn_step(IC<1>(), IC<1>(), cB, 15, 6, nop, [&] { glu(cA, 32, 0, 0, 8); });
      ffn_step(IC<1>(), IC<1>(), cB, 16, 7, nop, [&] { glu(cA, 32, 0, 8, 16); });
      ffn_step(IC<0>(), IC<1>(), cC, 17, 0, [&] { fence_regs<0, 64>(cB); }, nop);
      if (tid == 0) PROF_EV(4);
      ffn_step(IC<1>(), IC<1>(), cC, 18, 1, nop, [&] { glu(cB, 32, 16, 0, 8); });
      ffn_step(IC<1>(), IC<1>(), cC, 19, 2, nop, [&] { glu(cB, 32, 16, 8, 16); });
#pragma unroll 1
      for (int kb = 3; kb < 8; kb++) ffn_step(IC<1>(), IC<1>(), cC, 17 + kb, kb, nop, nop);
      if (tid == 0) PROF_EV(5);
      auto m_step = [&](auto first, int i, auto done, auto work) {
        acquire(25 + i);
        wg_fence();
        const uint64_t dx = d128(dX + i * 2048), dm = d64(dN + RING + rslot(25 + i) * 1024);
        mma_ss64<0, 1, decltype(first)::value>(ct, dx, dm);
        mma_ss64<0, 1, 1>(ct, dx + 2, dm + 64);
        wg_commit();
        work();
        wg_wait<1>();
        freeP(25 + i);
        done();
        wg_fence();
#pragma unroll
        for (int k = 2; k < 8; k++) mma_ss64<0, 1, 1>(ct, dx + ((k >> 2) * 1024 + (k & 3) * 2), dm + k * 64);
        wg_commit();
      };
      auto freeT = [&](int t) { mbar_arrive_if(elect, bars + 8 * (B_ET + t)); };
      m_step(IC<0>(), 0, [&] { fence_regs<0, 64>(cC); }, nop);
      m_step(IC<1>(), 1, [&] { freeT(0); }, [&] { glu(cC, 32, 32, 0, 5); });
      m_step(IC<1>(), 2, [&] { freeT(1); }, [&] { glu(cC, 32, 32, 5, 11); });
      m_step(IC<1>(), 3, [&] { freeT(2); }, [&] { glu(cC, 32, 32, 11, 16); });
      waitA(29 + wg);
      if (tid == 0) PROF_EV(6);
      mbar_wait(bars + 8 * (j == 0 ? B_T : B_TL), 0);
      if (tid == 0) PROF_EV(7);
      wg_fence();
      {
        const uint64_t dt = d128(dN + (OFF_T >> 4) + wg * 512), de = d128(dK + RING + (1 + wg) * 1024);
        mma_ss64<0, 1, 0>(ci, de, dt);
        mma_ss64<32, 1, 0>(ci, de + 512, dt);
#pragma unroll
        for (int k = 1; k < 4; k++) {
          mma_ss64<0, 1, 1>(ci, de + k * 2, dt + k * 128);
          mma_ss64<32, 1, 1>(ci, de + (512 + k * 2), dt + k * 128);
        }
        wg_commit();
        wg_wait<1>();
        freeT(3);
        fence_regs<0, 32>(ct);
        glu(ct, 16, 48, 0, 8);
      }

      auto head = [&](auto off, int t, auto first) {
        constexpr int O = decltype(off)::value;
        mbar_wait(bars + 8 * (B_FT + (t & 3)), t >> 2);
        const uint64_t db = d128(dN + (t & 3) * (TB >> 4) + rank * 256);
        wg_fence();
        mma_rs64<O, 1, decltype(first)::value>(ct, h[0], h[1], h[2], h[3], db, zero);
#pragma unroll
        for (int k = 1; k < 6; k++) mma_rs64<O, 1, 1>(ct, h[4 * k], h[4 * k + 1], h[4 * k + 2], h[4 * k + 3], db + k * 128);
        wg_commit();
        wg_wait<1>();
      };
      auto rest = [&](auto off, int t) {
        constexpr int O = decltype(off)::value;
        const uint64_t db = d128(dN + (t & 3) * (TB >> 4)), dw = db + rank * 256, dm = db + (rank ? 0 : 1536);
        wg_fence();
#pragma unroll
        for (int k = 6; k < 12; k++) mma_rs64<O, 1, 1>(ct, h[4 * k], h[4 * k + 1], h[4 * k + 2], h[4 * k + 3], dw + k * 128);
#pragma unroll
        for (int k = 0; k < 2; k++) mma_rs64<O, 1, 1>(ct, h[48 + 4 * k], h[49 + 4 * k], h[50 + 4 * k], h[51 + 4 * k], dm + k * 128);
#pragma unroll
        for (int k = 0; k < 4; k++) mma_rs64<O, 1, 1>(ct, yf[4 * k], yf[4 * k + 1], yf[4 * k + 2], yf[4 * k + 3], db + (14 + k) * 128);
        wg_commit();
      };
      const uint32_t peerZ = mapa(sb + OFF_Z + tid * 16, rank ^ 1), peerB = mapa(bars + 8 * B_Z, rank ^ 1);
      auto send = [&](auto off, int t) {
        constexpr int O = decltype(off)::value;
        fence_regs<O, 32>(ct);
        const bool grid = t >= 3 && t < 6;
        const int z = grid ? t - 3 : t == 6 ? 3 : t;
        if (grid) {
          mbar_wait(bars + 8 * (B_Z + z), 0);
#pragma unroll
          for (int i = 0; i < 4; i++) {
            const uint4 p = *(const uint4*)(smem + OFF_Z + z * U + i * 4096 + tid * 16);
            const uint32_t a[4] = {p.x, p.y, p.z, p.w};
#pragma unroll
            for (int e = 0; e < 4; e++) { ct[O + 8 * i + 2 * e] += bf_lo(a[e]); ct[O + 8 * i + 2 * e + 1] += bf_hi(a[e]); }
          }
        }
        uint32_t pk[16];
#pragma unroll
        for (int i = 0; i < 16; i++) pk[i] = pack_bf16(ct[O + 2 * i], ct[O + 2 * i + 1]);
        if (grid) {
          const int owner = rb * 8 + 2 * ((q4 + z + 1) & 3) + rank;
          uint4* dst = g_part + (size_t)(owner * 3 + z) * 1024 + tid;
#pragma unroll
          for (int i = 0; i < 4; i++) st_x4(dst + i * 256, (pk[4 * i] & ~1u) | tag, pk[4 * i + 1], pk[4 * i + 2], pk[4 * i + 3]);
          __syncwarp();
          hint_add_if(lane == 0, &g_cntP[32 * owner + z]);
        } else {
#pragma unroll
          for (int i = 0; i < 4; i++)
            asm volatile("st.async.weak.shared::cluster.mbarrier::complete_tx::bytes.v4.b32 [%0], {%1,%2,%3,%4}, [%5];" ::"r"(peerZ + z * U + i * 4096),
                         "r"(pk[4 * i]), "r"(pk[4 * i + 1]), "r"(pk[4 * i + 2]), "r"(pk[4 * i + 3]), "r"(peerB + 8 * z) : "memory");
        }
      };
      asm volatile("barrier.cluster.wait.aligned;" ::: "memory");
      head(IC<0>(), 0, IC<2>());
      if (elect) asm volatile("mbarrier.arrive.shared::cluster.b64 _, [%0];" ::"r"(mapa(bars + 8 * B_RDY, rank ^ 1)) : "memory");
      fence_regs<0, 64>(ci);
#pragma unroll
      for (int i = 0; i < 16; i++) {
        const float gg = ((i & 1) ? g1 : g0) * (2.0f / (2048.0f * 512.0f));
        if (i & 2) yf[i] = pack_pin((ci[2 * i] - ci[28 + 2 * i]) * gg, (ci[2 * i + 1] - ci[29 + 2 * i]) * gg);
        else yf[i] = pack_pin((ci[2 * i] + ci[36 + 2 * i]) * gg, (ci[2 * i + 1] + ci[37 + 2 * i]) * gg);
      }
      if (tid == 0) PROF_EV(8);
#pragma unroll 1
      for (int t = 0;; t += 2) {
        rest(IC<0>(), t);
        head(IC<32>(), t + 1, IC<2>());
        mbar_arrive_if(elect && t < 6, bars + 8 * (B_ET + t));
        if (t == 0) mbar_wait(bars + 8 * B_RDY, 0);
        send(IC<0>(), t);
        rest(IC<32>(), t + 1);
        if (t == 6) break;
        head(IC<0>(), t + 2, IC<2>());
        mbar_arrive_if(elect, bars + 8 * (B_ET + t + 1));
        send(IC<32>(), t + 1);
      }
      if (tid == 0) PROF_EV(9);
      {
        float sum[32];
        mbar_wait(bars + 8 * (B_Z + 3), 0);
#pragma unroll
        for (int i = 0; i < 4; i++) {
          const uint4 p = *(const uint4*)(smem + OFF_Z + 3 * U + i * 4096 + tid * 16);
          const uint32_t a[4] = {p.x, p.y, p.z, p.w};
#pragma unroll
          for (int e = 0; e < 4; e++) { sum[8 * i + 2 * e] = bf_lo(a[e]); sum[8 * i + 2 * e + 1] = bf_hi(a[e]); }
        }
#pragma unroll 1
        for (int z = 0; z < 3; z++) {
          mbar_wait(bars + 8 * (B_HP + z), 0);
          if (z == 2 && tid == 0) PROF_EV(24);
          uint4 pv[4];
#pragma unroll
          for (int i = 0; i < 4; i++) pv[i] = *(const uint4*)(smem + z * U + i * 4096 + tid * 16);
          const uint32_t t0 = (uint32_t)clock();
          while (__any_sync(0xffffffffu, ((pv[0].x ^ tag) | (pv[1].x ^ tag) | (pv[2].x ^ tag) | (pv[3].x ^ tag)) & 1)) {
#pragma unroll
            for (int i = 0; i < 4; i++) pv[i] = ld_x4(g_part + (size_t)((rb * 8 + j) * 3 + z) * 1024 + tid + i * 256);
            spin_guard(t0);
          }
#pragma unroll
          for (int i = 0; i < 4; i++) {
            const uint32_t a[4] = {pv[i].x & ~1u, pv[i].y, pv[i].z, pv[i].w};
#pragma unroll
            for (int e = 0; e < 4; e++) { sum[8 * i + 2 * e] += bf_lo(a[e]); sum[8 * i + 2 * e + 1] += bf_hi(a[e]); }
          }
        }
        if (tid == 0) PROF_EV(14);
        wg_wait<0>();
        fence_regs<32, 32>(ct);
#pragma unroll
        for (int i = 0; i < 32; i++) sum[i] += ct[32 + i];
        const uint32_t stg = sb + OFF_T + warp * 2048;
        const int mr = (lane & 7) + ((lane >> 3) & 1) * 8, mc = lane >> 4;
#pragma unroll
        for (int i = 0; i < 4; i++) {
          const uint32_t a = stg + mr * 128 + (((2 * i + mc) ^ (mr & 7)) << 4);
          asm volatile("stmatrix.sync.aligned.m8n8.x4.shared.b16 [%0], {%1,%2,%3,%4};" ::"r"(a), "r"(pack_bf16(sum[8 * i], sum[8 * i + 1])),
                       "r"(pack_bf16(sum[8 * i + 2], sum[8 * i + 3])), "r"(pack_bf16(sum[8 * i + 4], sum[8 * i + 5])),
                       "r"(pack_bf16(sum[8 * i + 6], sum[8 * i + 7])) : "memory");
        }
        __syncwarp();
#pragma unroll
        for (int i = 0; i < 4; i++) {
          const int r = 4 * i + (lane >> 3), c = lane & 7;
          const uint4 v = *(const uint4*)(smem + OFF_T + warp * 2048 + r * 128 + ((c ^ (r & 7)) << 4));
          *(uint4*)(out + (size_t)(2 * rb + wg + 32 * (16 * w + r)) * 512 + 64 * j + 8 * c) = v;
        }
      }
      if (tid == 0) { PROF_EV(15); PROF_CK(41); }
    }
  } else if (warp < 12) {
    asm volatile("setmaxnreg.dec.sync.aligned.u32 104;");
    asm volatile("barrier.cluster.arrive.relaxed.aligned;" ::: "memory");
    const int t = tid - 256, w = warp - 8;
    const uint32_t ep = ld_x1(&g_epoch[blockIdx.x * 8]);
    const uint32_t tag = (ep + 1) & 1;
    auto gate_rows = [&] {
      const int r = 16 * j + 4 * w + (lane >> 3);
      const uint4* px = (const uint4*)(x + (size_t)(2 * rb + (r >> 6) + 32 * (r & 63)) * 512) + (lane & 7);
      const uint4* pg = (const uint4*)gate_w + (lane & 7);
      {
        float a = 0.f;
#pragma unroll 1
        for (int i = 0; i < 8; i += 4) {
          uint4 u[4], v[4];
#pragma unroll
          for (int e = 0; e < 4; e++) { u[e] = __ldg(px + (i + e) * 8); v[e] = __ldg(pg + (i + e) * 8); }
#pragma unroll
          for (int e = 0; e < 4; e++) {
            a = fmaf(bf_lo(u[e].x), bf_lo(v[e].x), a); a = fmaf(bf_hi(u[e].x), bf_hi(v[e].x), a);
            a = fmaf(bf_lo(u[e].y), bf_lo(v[e].y), a); a = fmaf(bf_hi(u[e].y), bf_hi(v[e].y), a);
            a = fmaf(bf_lo(u[e].z), bf_lo(v[e].z), a); a = fmaf(bf_hi(u[e].z), bf_hi(v[e].z), a);
            a = fmaf(bf_lo(u[e].w), bf_lo(v[e].w), a); a = fmaf(bf_hi(u[e].w), bf_hi(v[e].w), a);
          }
        }
#pragma unroll
        for (int o = 4; o; o >>= 1) a += __shfl_xor_sync(0xffffffffu, a, o);
        if ((lane & 7) == 0)
          asm volatile("st.relaxed.gpu.global.f32 [%0], %1;" ::"l"(g_gate + rb * 128 + r), "f"(tagf(__fdividef(1.0f, 1.0f + __expf(-a)), tag)) : "memory");
        if (t == 0) PROF_EV(18);
      }
      if (w == 0) {
        const int c = lane >> 4, jj = 16 * blockIdx.x + (lane & 15), jm = (2048 - jj) & 2047;
        const unsigned short* pr = (const unsigned short*)w_r + 256 * c;
        const unsigned short* pi = (const unsigned short*)w_i + 256 * c;
        const float wr = 0.25f * (bf_lo(__ldg(pr + jj * 257)) + bf_lo(__ldg(pr + jm * 257)));
        const float wi = 0.25f * (bf_lo(__ldg(pi + jj * 257)) - bf_lo(__ldg(pi + jm * 257)));
        st_u2(g_Wh + c * 2048 + jj, c ? pack_bf16(-wi, wr) : pack_bf16(wr, wi), tag);
        __syncwarp();
        hint_add_if(lane == 0, &g_cntW[0]);
      }
    };
    {
      const int g = lane >> 2, q = lane & 3;
      uint32_t wf[32];
      if (!helper) {
        asm volatile("bar.sync 4, 256;" ::: "memory");
        mbar_wait(bars + 8 * (B_FX + GATE_AT), 0);
        gate_rows();
        const uint32_t wa = sb + OFF_T + w * (3072 + 4) + q * 48 + g * 2;
        mbar_wait(bars + 8 * (B_FE + 3), 0);
        if (t == 0) PROF_EV(32);
        if (WPACE) __nanosleep(WPACE * w);
#pragma unroll 1
        for (int ri = 0; ri < 2; ri++) {
          if (lane == 0) {
            mbar_expect_tx(bars + 8 * (B_WR + w), 3072);
            tma4d(sb + OFF_T + w * 3072, ri ? &maps.wi : &maps.wr, bars + 8 * (B_WR + w), 16 * kg, 0, 2 * w, tn);
          }
          if (ri) {
            const uint32_t t0 = (uint32_t)clock();
            uint32_t v;
            do { v = ld_x1(g_gate + rb * 128 + t); spin_guard(t0); } while (__any_sync(0xffffffffu, (v ^ tag) & 1));
            *(uint32_t*)(smem + OFF_G + t * 4) = v;
            __syncwarp();
            mbar_arrive_if(lane == 0, bars + 8 * B_G);
          }
          mbar_wait(bars + 8 * (B_WR + w), ri);
#pragma unroll
          for (int n2 = 0; n2 < 4; n2++) {
            uint32_t v[8];
#pragma unroll
            for (int i = 0; i < 8; i++)
              asm volatile("ld.shared.u16 %0, [%1];" : "=r"(v[i]) : "r"(wa + (2 * n2 + ((i >> 1) & 1)) * 192 + (i & 1) * (1536 + 2) + (i >> 2) * 16) : "memory");
#pragma unroll
            for (int i = 0; i < 8; i++) {
              uint32_t& d = wf[(i >> 2) * 16 + 4 * n2 + (i & 3)];
              d = __byte_perm(d, v[i], 0x5432);
              if (WBATCH) asm volatile("" : "+r"(d)::"memory");
            }
          }
          __syncwarp();
        }
        asm volatile("bar.sync 1, 128;" ::: "memory");
        if (t == 0) PROF_EV(11);
      } else {
        asm volatile("bar.sync 4, 256;" ::: "memory");
        hint_wait(&g_cntW[0], (ep + 1) * 128u);
        const uint32_t t0 = (uint32_t)clock();
#pragma unroll 1
        for (;;) {
          uint32_t bad = 0;
#pragma unroll
          for (int i = 0; i < 32; i++) {
            const float2 v = ld_x2((const float2*)g_Wh + (i >> 4) * 2048 + 16 * w + g + 8 * (i & 1) + 64 * q + ((i >> 1) & 7) * 256);
            wf[i] = __float_as_uint(v.x); bad |= __float_as_uint(v.y) ^ tag;
          }
          if (!__any_sync(0xffffffffu, bad & 1)) break;
          spin_guard(t0);
        }
        if (t == 0) PROF_EV(11);
      }
      if (t == 0) { mbar_expect_tx(bars + 8 * B_W, 8192); bulk_load(sb + OFF_D, g_DT.v, 8192, bars + 8 * B_W); }
      mbar_wait(bars + 8 * B_W, 0);
      mbar_wait(bars + 8 * B_HX, 0);
      if (t == 0) PROF_EV(12);
      const uint32_t dd = (sb & 0x3FFFF) >> 4;
      const uint64_t dF = d128((dd + (OFF_D >> 4)) | (512u << 16)), dI = d128((dd + (OFF_D >> 4)) | (1u << 16)), dA = d128((dd + (OFF_XB >> 4)) | (512u << 16));
      float az[32];
      const int zero = blockIdx.x >> 16;
      uint32_t pf[32];
#pragma unroll
      for (int mt = 0; mt < 2; mt++) {
        wg_fence();
        if (mt == 0) mma_ss64<0, 3, 0>(az, dA, dF);
        else mma_ss64<0, 3, 2>(az, dA + 512, dF, zero);
#pragma unroll
        for (int k = 1; k < 4; k++) mma_ss64<0, 3, 1>(az, dA + (mt * 512 + k * 128), dF + k * 128);
        wg_commit();
        wg_wait<0>();
        fence_regs<0, 32>(az);
#pragma unroll
        for (int i = 0; i < 16; i++) {
          const float wr = bf_lo(wf[16 * mt + i]), wi = bf_hi(wf[16 * mt + i]);
          pf[16 * mt + i] = pack_pin(fmaf(az[2 * i], wr, -az[2 * i + 1] * wi), fmaf(az[2 * i], wi, az[2 * i + 1] * wr));
        }
      }
      if (t == 0) PROF_EV(16);
#pragma unroll
      for (int mt = 0; mt < 2; mt++) {
        wg_fence();
        mma_rs64<0, 0, 2>(az, pf[16 * mt], pf[16 * mt + 1], pf[16 * mt + 2], pf[16 * mt + 3], dI, mt ? (int)helper : zero);
#pragma unroll
        for (int k = 1; k < 4; k++) mma_rs64<0, 0, 1>(az, pf[16 * mt + 4 * k], pf[16 * mt + 4 * k + 1], pf[16 * mt + 4 * k + 2], pf[16 * mt + 4 * k + 3], dI + k * 2);
        wg_commit();
        wg_wait<0>();
        fence_regs<0, 32>(az);
        if (!helper) {
          const int m = lane >> 3, r = lane & 7;
          const int sl = 2 * (m >> 1) + ((r >> 1) & 1) + 4 * (r >> 2);
          const uint32_t a0 = sb + OFF_XB + (2 * w + (m & 1)) * 2048 + sl * 64 + (((mt * 2 + (r & 1)) ^ (sl >> 1)) << 4);
#pragma unroll
          for (int i = 0; i < 4; i++)
            stsm4t(a0 + i * 512, pack_bf16(az[8 * i], az[8 * i + 1]), pack_bf16(az[8 * i + 2], az[8 * i + 3]), pack_bf16(az[8 * i + 4], az[8 * i + 5]),
                   pack_bf16(az[8 * i + 6], az[8 * i + 7]));
        }
      }
      if (helper) {
#pragma unroll
        for (int i = 0; i < 16; i++) {
          const int n = i >> 1, s0 = 8 * (n >> 1) + 2 * (n & 1) + (q & 1) + 4 * (q >> 1);
          if ((n & 1) == (int)(blockIdx.x & 1)) st_u2(g_Ts + s0 * 64 + 16 * w + g + 8 * (i & 1), pack_bf16(az[2 * i], az[2 * i + 1]), tag);
        }
        __syncwarp();
        hint_add_if(lane == 0, &g_cntH[0]);
        if (t == 0) { g_epoch[blockIdx.x * 8] = ep + 1; PROF_EV(13); }
      } else {
        asm volatile("fence.proxy.async.shared::cta;" ::: "memory");
        __syncwarp();
        if (lane == 0) {
          if (t == 0) PROF_EV(17);
          if (SPACE) __nanosleep(SPACE * w);
          asm volatile("cp.async.bulk.tensor.3d.global.shared::cta.bulk_group [%0, {%2, %3, %4}], [%1];" ::"l"(&maps.ts), "r"(sb + OFF_XB + w * 4096),
                       "r"(32 * kg), "r"(0), "r"(8 * tn + 2 * w) : "memory");
          bulk_done_signal(&g_cntT[32 * j]);
          if (t == 96) PROF_EV(13);
        }
        __syncwarp();
        if (j == 0) {
          hint_wait(&g_cntH[0], (ep + 1) * 8u);
          const uint32_t t0 = (uint32_t)clock();
          float2 v;
          do { v = ld_x2((const float2*)g_Ts + 2 * rb * 64 + t); spin_guard(t0); } while (__any_sync(0xffffffffu, (__float_as_uint(v.y) ^ tag) & 1));
          mbar_wait(bars + 8 * B_TL, 0);
          const uint32_t u = __float_as_uint(v.x);
          *(uint16_t*)(smem + OFF_T + t * 128 + ((t & 7) << 4)) = (uint16_t)u;
          *(uint16_t*)(smem + OFF_T + t * 128 + (((t & 7) ^ 1) << 4)) = (uint16_t)(u >> 16);
          asm volatile("fence.proxy.async.shared::cta;" ::: "memory");
          __syncwarp();
          mbar_arrive_if(lane == 0, bars + 8 * B_T);
        }
      }
    }
  } else {
    asm volatile("setmaxnreg.dec.sync.aligned.u32 24;");
    auto xf_load = [&](int q) {
      const uint32_t fb = bars + 8 * (B_FX + q);
      mbar_expect_tx(fb, U + 8192);
      tma3d(sb + q * U, &maps.x, fb, 64 * q, 0, 2 * rb);
      if (q >= 4) mbar_wait(bars + 8 * (B_FE + ((q - 4) >> 1)), 0);
      tma2d(sb + OFF_XB + (q & 3) * 8192, &maps.ft, fb, 64 * q, 64 * j);
    };
    if (lane == 0) {
      if (warp == 14) {
#pragma unroll
        for (int i = 0; i < B_FT; i++) mbar_init(bars + 8 * i, 1);
        asm volatile("fence.proxy.async.shared::cta;" ::: "memory");
        if (!helper) {
#pragma unroll 1
          for (int n = 0; n < 2; n++) {
            const uint32_t fb = bars + 8 * (B_FA + n);
            xf_load(2 * n); xf_load(2 * n + 1);
            mbar_expect_tx(fb, U);
            tma2d(sb + OFF_RING + n * U, &maps.g64, fb, f_full, 64 * n);
            tma2d(sb + OFF_RING + n * U + 8192, &maps.u64, fb, f_full, 64 * n);
          }
        }
      } else if (warp == 15) {
#pragma unroll
        for (int i = B_FT; i < NBAR; i++) mbar_init(bars + 8 * i, i < B_EA ? 1 : i < B_T ? 2 : 4);
#pragma unroll
        for (int i = 0; i < 4; i++) mbar_expect_tx(bars + 8 * (B_Z + i), U);
        asm volatile("fence.mbarrier_init.release.cluster;" ::: "memory");
        asm volatile("fence.proxy.async.shared::cta;" ::: "memory");
      } else if (warp == 13) {
#pragma unroll
        for (int i = 1; i < 4; i++) asm volatile("prefetch.tensormap [%0];" ::"l"((const char*)&maps + i * 128) : "memory");
      }
    }
    __syncwarp();
    asm volatile("bar.arrive 0, 384;" ::: "memory");
    asm volatile("bar.arrive 4, 256;" ::: "memory");
    __syncwarp();
    asm volatile("barrier.cluster.arrive.relaxed.aligned;" ::: "memory");
    asm volatile("bar.sync 3, 128;" ::: "memory");
    if (lane == 0 && (!helper || warp == 15)) {
      if (warp < 14) {
        const int p = warp - 12;
#pragma unroll 1
        for (int n = 2; n < 31; n++) {
          const bool table = n == 4 || n >= 29;
          const int q = n < 4 ? n : n - 1;
          const CUtensorMap* m = table ? &maps.e : n >= 25 ? &maps.g32 + p : &maps.g64 + p;
          const int c0 = table ? 0 : n >= 25 ? f_half : f_full + 64 * (q >> 3);
          const int c1 = table ? (2 * rb + ((n & 1) ^ 1)) * 128 + 64 * p : n >= 25 ? 128 * (n - 25) : 64 * (q & 7);
          const uint32_t fb = bars + 8 * (B_FA + (n & 3)), dst = sb + OFF_RING + (n & 3) * U + p * 8192;
          if (n < 4) mbar_wait(bars + 8 * (B_FE + n - 2), 0);
          else mbar_wait(bars + 8 * (B_EA + (n & 3)), ((n >> 2) & 1) ^ 1);
          tma2d(dst, m, fb, c0, c1);
          if (p == 0) mbar_expect_tx(fb, U);
        }
      } else if (warp == 15) {
        const unsigned ep1 = ld_x1(&g_epoch[blockIdx.x * 8]) + 1;
        flag_wait(&g_cntX[helper ? 0 : 32 * j], ep1 * 16u);
        PROF_EV(22);
        mbar_expect_tx(bars + 8 * B_HX, U);
        bulk_load(sb + OFF_XB, g_X + (size_t)(helper ? 128 : kg * 8 + tn) * 8192, U, bars + 8 * B_HX);
        if (!helper) {
          flag_wait(&g_cntT[32 * j], ep1 * 64u);
          PROF_EV(23);
          mbar_expect_tx(bars + 8 * B_TL, U);
          tma3d(sb + OFF_T, &maps.t, bars + 8 * B_TL, 64 * j, 0, 2 * rb);
#pragma unroll 1
          for (int i = 0; i < 3; i++) {
            mbar_wait(bars + 8 * (B_PZ + (i >> 1)), 0);
            flag_wait(&g_cntP[32 * (rb * 8 + j) + i], ep1 * 8u);
            mbar_expect_tx(bars + 8 * (B_HP + i), U);
            bulk_load(sb + i * U, g_part + (size_t)((rb * 8 + j) * 3 + i) * 1024, U, bars + 8 * (B_HP + i));
          }
          g_epoch[blockIdx.x * 8] = ep1;
        }
      } else {
#pragma unroll 1
        for (int q = 4; q < 8; q++) xf_load(q);
        mbar_wait(bars + 8 * (B_FE + 2), 0);
        mbar_expect_tx(bars + 8 * B_E0, U);
        tma2d(sb + OFF_XB, &maps.e, bars + 8 * B_E0, 0, 2 * rb * 128);
        tma2d(sb + OFF_XB + 8192, &maps.e, bars + 8 * B_E0, 0, 2 * rb * 128 + 64);
#pragma unroll 1
        for (int h2 = 0; h2 < 2; h2++) {
          const int s0 = 2 * rb + h2, sg = (s0 & ~6) | ((s0 & 2) << 1) | ((s0 & 4) >> 1);
          mbar_wait(bars + 8 * (B_XS + h2), 0);
#pragma unroll 1
          for (int c = 0; c < 2; c++) {
            asm volatile("cp.async.bulk.tensor.4d.global.shared::cta.bulk_group [%0, {%2, %3, %4, %5}], [%1];" ::"l"(&maps.xs),
                         "r"(sb + OFF_XB + h2 * 8192 + c * 4096), "r"(0), "r"(sg), "r"(0), "r"(16 * j + 8 * c) : "memory");
            if (j == 0)
              asm volatile("cp.async.bulk.global.shared::cta.bulk_group [%0], [%1], 256;" ::"l"(g_X + 128 * 8192 + c * 4096 + sg * 128),
                           "r"(sb + OFF_SP + h2 * 512 + c * 256) : "memory");
            if (SPACE && h2 + c < 2) __nanosleep(SPACE);
          }
        }
        bulk_done_signal(&g_cntX[32 * j]);
        PROF_EV(20);
#pragma unroll 1
        for (int t = 0; t < 8; t++) {
          const int i = t < 3 ? t + 1 : t < 6 ? t - 2 : 0;
          const int col = 64 * (2 * ((q4 + i) & 3) + ((t < 3 || t == 6) ? 1 - rank : rank));
          const uint32_t fb = bars + 8 * (B_FT + (t & 3)), dst = sb + (t & 3) * TB;
          mbar_wait(bars + 8 * (B_ET + (t == 2 ? 3 : t & 3)), t >> 2);
          mbar_expect_tx(fb, TB);
          tma2d(dst, &maps.d224, fb, col, 224 * j);
          if (t < 2) mbar_wait(bars + 8 * (B_ET + t + 1), 0);
          tma2d(dst + 28672, &maps.ft, fb, col, 64 * j);
        }
      }
    }
  }
}

typedef CUresult (*EncodeFn)(CUtensorMap*, CUtensorMapDataType, cuuint32_t, void*, const cuuint64_t*, const cuuint64_t*, const cuuint32_t*,
                             const cuuint32_t*, CUtensorMapInterleave, CUtensorMapSwizzle, CUtensorMapL2promotion, CUtensorMapFloatOOBfill);

static void encode(EncodeFn f, CUtensorMap* m, const void* base, int rank, const cuuint64_t* dims, const cuuint64_t* strides, const cuuint32_t* box,
                   CUtensorMapSwizzle sw) {
  cuuint32_t es[5] = {1, 1, 1, 1, 1};
  f(m, CU_TENSOR_MAP_DATA_TYPE_BFLOAT16, rank, (void*)base, dims, strides, box, es, CU_TENSOR_MAP_INTERLEAVE_NONE, sw,
    CU_TENSOR_MAP_L2_PROMOTION_L2_128B, CU_TENSOR_MAP_FLOAT_OOB_FILL_NONE);
}

extern "C" void kernel_launch(void* const* d_in, const int* in_sizes, int n_in, void* d_out, int out_size) {
  (void)in_sizes; (void)n_in; (void)out_size;
  const __nv_bfloat16* x = (const __nv_bfloat16*)d_in[0];
  const __nv_bfloat16* w_r = (const __nv_bfloat16*)d_in[1];
  const __nv_bfloat16* w_i = (const __nv_bfloat16*)d_in[2];
  const __nv_bfloat16* Wg = (const __nv_bfloat16*)d_in[4];
  const __nv_bfloat16* Wu = (const __nv_bfloat16*)d_in[5];
  const __nv_bfloat16* Wd = (const __nv_bfloat16*)d_in[6];
  const __nv_bfloat16* gw = (const __nv_bfloat16*)d_in[7];

  void* fp = nullptr; cudaDriverEntryPointQueryResult qr;
  cudaGetDriverEntryPoint("cuTensorMapEncodeTiled", &fp, cudaEnableDefault, &qr);
  EncodeFn enc = (EncodeFn)fp;
  void *pFT, *pET, *pX, *pT;
  cudaGetSymbolAddress(&pX, g_X); cudaGetSymbolAddress(&pT, g_T);
  cudaGetSymbolAddress(&pFT, g_FT); cudaGetSymbolAddress(&pET, g_ET);

  Maps mp;
  const CUtensorMapSwizzle S128 = CU_TENSOR_MAP_SWIZZLE_128B, S64 = CU_TENSOR_MAP_SWIZZLE_64B;
  { cuuint64_t d[3] = {512, 64, 32}, s[2] = {32768, 1024}; cuuint32_t b[3] = {64, 64, 2}; encode(enc, &mp.x, x, 3, d, s, b, S128); }
  { cuuint64_t d[2] = {512, 512}, s[1] = {1024}; cuuint32_t b[2] = {64, 64}; encode(enc, &mp.ft, pFT, 2, d, s, b, S128); }
  { cuuint64_t d[4] = {128, 32, 2, 129}, s[3] = {256, 8192, 16384}; cuuint32_t b[4] = {128, 1, 2, 8}; encode(enc, &mp.xs, pX, 4, d, s, b, CU_TENSOR_MAP_SWIZZLE_NONE); }
  { cuuint64_t d[3] = {512, 32, 64}, s[2] = {65536, 1024}; cuuint32_t b[3] = {32, 32, 2}; encode(enc, &mp.ts, pT, 3, d, s, b, S64); }
  { cuuint64_t d[3] = {512, 64, 32}, s[2] = {1024, 65536}; cuuint32_t b[3] = {64, 64, 2}; encode(enc, &mp.t, pT, 3, d, s, b, S128); }
  { cuuint64_t d[2] = {64, 4096}, s[1] = {128}; cuuint32_t b[2] = {64, 64}; encode(enc, &mp.e, pET, 2, d, s, b, S128); }
  { cuuint64_t d[2] = {1792, 512}, s[1] = {3584}; cuuint32_t b[2] = {64, 64}, b2[2] = {32, 128};
    encode(enc, &mp.g64, Wg, 2, d, s, b, S128); encode(enc, &mp.u64, Wu, 2, d, s, b, S128);
    encode(enc, &mp.g32, Wg, 2, d, s, b2, S64); encode(enc, &mp.u32, Wu, 2, d, s, b2, S64); }
  { cuuint64_t d[2] = {512, 1792}, s[1] = {1024}; cuuint32_t b[2] = {64, 224}; encode(enc, &mp.d224, Wd, 2, d, s, b, S128); }
  { cuuint64_t d[4] = {264, 32, 8, 8}, s[3] = {32896, 512, 4112}; cuuint32_t b[4] = {24, 32, 2, 1};
    encode(enc, &mp.wr, w_r, 4, d, s, b, CU_TENSOR_MAP_SWIZZLE_NONE); encode(enc, &mp.wi, w_i, 4, d, s, b, CU_TENSOR_MAP_SWIZZLE_NONE); }

  cudaFuncSetAttribute(fused_kernel, cudaFuncAttributeMaxDynamicSharedMemorySize, SMEM_BYTES);
  fused_kernel<<<NCTA, 512, SMEM_BYTES>>>(mp, x, w_r, w_i, gw, (__nv_bfloat16*)d_out);
}
```

```cpp
#include <cuda_runtime.h>
#include <cuda_bf16.h>
#include <cuda.h>
#include <stdint.h>

namespace tbl {
constexpr double PI = 3.14159265358979323846264338327950288;
constexpr double sin_s(double x) { double t = x, s = x; for (int n = 1; n < 12; n++) { t *= -x * x / ((2 * n) * (2 * n + 1)); s += t; } return s; }
constexpr double cos_s(double x) { double t = 1, s = 1; for (int n = 1; n < 12; n++) { t *= -x * x / ((2 * n - 1) * (2 * n)); s += t; } return s; }
constexpr double cos2048(int m) {
  m &= 2047; if (m > 1024) m = 2048 - m;
  bool neg = false; if (m > 512) { m = 1024 - m; neg = true; }
  double v = (m <= 256) ? cos_s(2 * PI * m / 2048) : sin_s(2 * PI * (512 - m) / 2048);
  return neg ? -v : v;
}
constexpr uint16_t to_bf16(double v) {
  if (v == 0) return 0;
  uint16_t s = 0; if (v < 0) { s = 0x8000; v = -v; }
  int e = 0; while (v >= 2) { v /= 2; e++; } while (v < 1) { v *= 2; e--; }
  double m = (v - 1) * 128; int mi = (int)m; double fr = m - mi;
  if (fr > 0.5 || (fr == 0.5 && (mi & 1))) mi++;
  if (mi == 128) { mi = 0; e++; }
  return (uint16_t)(s | ((e + 127) << 7) | mi);
}
struct CosT { uint16_t v[2048]; constexpr CosT() : v() { for (int i = 0; i < 2048; i++) v[i] = to_bf16(cos2048(i)); } };
struct alignas(1024) FT {
  uint16_t v[512 * 512];
  constexpr FT() : v() {
    CosT c;
    for (int r = 0; r < 512; r++) {
      int k = (r >> 4) * 8 + (r & 7), e = (r >> 3) & 1;
      int mul = 4 * k, add = e ? 512 : 0;
      if (k == 0 && e == 1) { mul = 1024; add = 0; }
      for (int d = 0; d < 512; d++) v[r * 512 + d] = c.v[(d * mul + add) & 2047];
    }
  }
};
struct alignas(1024) ET {
  uint16_t v[2048 * 128];
  constexpr ET() : v() {
    CosT c;
    for (int s = 0; s < 2048; s++)
      for (int j = 0; j < 64; j++) {
        const int o = (s & 31) * 8192 + (s >> 5) * 64 + j;
        v[o] = c.v[(s * j) & 2047]; v[o + 4096] = c.v[(s * j + 512) & 2047];
      }
  }
};
struct alignas(1024) DT {
  uint16_t v[64 * 64];
  constexpr DT() : v() {
    CosT c;
    for (int r = 0; r < 64; r++)
      for (int n = 0; n < 64; n++) {
        const int sg = r >> 1, s0 = (sg & ~6) | ((sg & 2) << 1) | ((sg & 4) >> 1), e = r & 1, f = n & 1;
        const int m = 64 * s0 * (n >> 1) + (e == f ? 0 : e ? -512 : 512);
        v[r * 64 + (((n >> 3) ^ (r & 7)) << 3) + (n & 7)] = c.v[m & 2047];
      }
  }
};
}

__device__ constexpr tbl::FT g_FT = tbl::FT();
__device__ constexpr tbl::ET g_ET = tbl::ET();
__device__ constexpr tbl::DT g_DT = tbl::DT();

__device__ __align__(1024) uint16_t g_X[129 * 8192];
__device__ __align__(1024) uint16_t g_T[32 * 64 * 512];
__device__ __align__(1024) uint2 g_Ts[32 * 64];
__device__ __align__(1024) uint4 g_part[128 * 3 * 1024];
__device__ __align__(16) float g_gate[16 * 128];
__device__ __align__(16) uint2 g_Wh[2 * 2048];
__device__ unsigned g_epoch[132 * 8];
__device__ unsigned g_cntX[8 * 32], g_cntT[8 * 32], g_cntP[128 * 32], g_cntW[32], g_cntH[32];
#define PROF_EV(i) do {} while (0)
#define PROF_CK(i) do {} while (0)

__device__ __forceinline__ uint32_t smem_u32(const void* p) { return (uint32_t)__cvta_generic_to_shared(p); }
__device__ __forceinline__ void mbar_init(uint32_t bar, uint32_t cnt) { asm volatile("mbarrier.init.shared::cta.b64 [%0], %1;" ::"r"(bar), "r"(cnt)); }
__device__ __forceinline__ void mbar_expect_tx(uint32_t bar, uint32_t bytes) { asm volatile("mbarrier.arrive.expect_tx.shared::cta.b64 _, [%0], %1;" ::"r"(bar), "r"(bytes) : "memory"); }
__device__ __forceinline__ void mbar_arrive(uint32_t bar) { asm volatile("mbarrier.arrive.shared::cta.b64 _, [%0];" ::"r"(bar) : "memory"); }
__device__ __forceinline__ void mbar_arrive_if(bool p, uint32_t bar) {
  asm volatile("{\n.reg .pred p;\nsetp.ne.b32 p, %1, 0;\n@p mbarrier.arrive.shared::cta.b64 _, [%0];\n}" ::"r"(bar), "r"((int)p) : "memory");
}
__device__ __forceinline__ void hint_add_if(bool p, unsigned* a) {
  asm volatile("{\n.reg .pred p;\nsetp.ne.b32 p, %1, 0;\n@p red.relaxed.gpu.global.add.u32 [%0], 1;\n}" ::"l"(a), "r"((int)p) : "memory");
}
__device__ __forceinline__ bool mbar_try(uint32_t bar, uint32_t parity) {
  uint32_t ok;
  asm volatile("{\n.reg .pred p;\nmbarrier.test_wait.parity.shared::cta.b64 p, [%1], %2;\nselp.u32 %0, 1, 0, p;\n}" : "=r"(ok) : "r"(bar), "r"(parity) : "memory");
  return ok;
}
__device__ __forceinline__ void mbar_wait(uint32_t bar, uint32_t parity) {
  asm volatile(
      "{\n.reg .pred p;\n.reg .u32 n;\nmov.u32 n, 0;\n"
      "W_LOOP:\nmbarrier.try_wait.parity.shared::cta.b64 p, [%0], %1;\n@p bra W_DONE;\n"
      "add.u32 n, n, 1;\nsetp.lt.u32 p, n, 0x40000;\n@p bra W_LOOP;\ntrap;\nW_DONE:\n}" ::"r"(bar), "r"(parity) : "memory");
}
__device__ __forceinline__ void bulk_load(uint32_t dst, const void* src, uint32_t bytes, uint32_t bar) {
  asm volatile("cp.async.bulk.shared::cluster.global.mbarrier::complete_tx::bytes [%0], [%1], %2, [%3];" ::"r"(dst), "l"(src), "r"(bytes), "r"(bar) : "memory");
}
__device__ __forceinline__ void cp16(uint32_t dst, const void* src) { asm volatile("cp.async.cg.shared.global [%0], [%1], 16;" ::"r"(dst), "l"(src) : "memory"); }
__device__ __forceinline__ void spin_guard(uint32_t t0) { if ((uint32_t)clock() - t0 > (1u << 30)) __trap(); }
__device__ __forceinline__ float tagf(float v, uint32_t tag) { return __uint_as_float((__float_as_uint(v) & ~1u) | tag); }
__device__ __forceinline__ float untag(float v) { return __uint_as_float(__float_as_uint(v) & ~1u); }
__device__ __forceinline__ void st_x2(float2* p, float a, float b) { asm volatile("st.relaxed.gpu.global.v2.f32 [%0], {%1,%2};" ::"l"(p), "f"(a), "f"(b) : "memory"); }
__device__ __forceinline__ float2 ld_x2(const float2* p) { float2 v; asm volatile("ld.relaxed.gpu.global.v2.f32 {%0,%1}, [%2];" : "=f"(v.x), "=f"(v.y) : "l"(p) : "memory"); return v; }
__device__ __forceinline__ void st_u2(uint2* p, uint32_t a, uint32_t b) { asm volatile("st.relaxed.gpu.global.v2.u32 [%0], {%1,%2};" ::"l"(p), "r"(a), "r"(b) : "memory"); }
__device__ __forceinline__ void prefetch2d(const CUtensorMap* m, int c0, int c1) { asm volatile("cp.async.bulk.prefetch.tensor.2d.L2.global [%0, {%1, %2}];" ::"l"(m), "r"(c0), "r"(c1) : "memory"); }
__device__ __forceinline__ void prefetch1d(const void* p, uint32_t bytes) { asm volatile("cp.async.bulk.prefetch.L2.global [%0], %1;" ::"l"(p), "r"(bytes) : "memory"); }
__device__ __forceinline__ uint32_t ld_x1(const void* p) { uint32_t v; asm volatile("ld.relaxed.gpu.global.u32 %0, [%1];" : "=r"(v) : "l"(p) : "memory"); return v; }
__device__ __forceinline__ uint4 ld_x4(const void* p) { uint4 v; asm volatile("ld.relaxed.gpu.global.v4.u32 {%0,%1,%2,%3}, [%4];" : "=r"(v.x), "=r"(v.y), "=r"(v.z), "=r"(v.w) : "l"(p) : "memory"); return v; }
__device__ __forceinline__ void st_x4(void* p, uint32_t a, uint32_t b, uint32_t c, uint32_t d) { asm volatile("st.relaxed.gpu.global.v4.u32 [%0], {%1,%2,%3,%4};" ::"l"(p), "r"(a), "r"(b), "r"(c), "r"(d) : "memory"); }
__device__ __forceinline__ uint32_t mapa(uint32_t a, uint32_t cta) { uint32_t r; asm volatile("mapa.shared::cluster.u32 %0, %1, %2;" : "=r"(r) : "r"(a), "r"(cta)); return r; }
__device__ __forceinline__ void stsm4t(uint32_t a, uint32_t r0, uint32_t r1, uint32_t r2, uint32_t r3) {
  asm volatile("stmatrix.sync.aligned.m8n8.x4.trans.shared.b16 [%0], {%1,%2,%3,%4};" ::"r"(a), "r"(r0), "r"(r1), "r"(r2), "r"(r3) : "memory");
}
__device__ __forceinline__ void hint_add(unsigned* p) { asm volatile("red.relaxed.gpu.global.add.u32 [%0], 1;" ::"l"(p) : "memory"); }
__device__ __forceinline__ void hint_wait(const unsigned* p, unsigned target) {
  const uint32_t t0 = (uint32_t)clock();
  while ((int)(ld_x1(p) - target) < 0) spin_guard(t0);
}
__device__ __forceinline__ void bulk_done_signal(unsigned* p) {
  asm volatile("cp.async.bulk.commit_group;\ncp.async.bulk.wait_group 0;\nfence.proxy.async.global;" ::: "memory");
  hint_add(p);
}
__device__ __forceinline__ void flag_wait(const unsigned* p, unsigned target) {
  hint_wait(p, target);
  asm volatile("fence.proxy.async.global;" ::: "memory");
}
__device__ __forceinline__ void tma2d(uint32_t dst, const CUtensorMap* m, uint32_t bar, int c0, int c1) {
  asm volatile("cp.async.bulk.tensor.2d.shared::cluster.global.mbarrier::complete_tx::bytes [%0], [%1, {%3, %4}], [%2];" ::"r"(dst), "l"(m), "r"(bar), "r"(c0), "r"(c1) : "memory");
}
__device__ __forceinline__ void tma3d(uint32_t dst, const CUtensorMap* m, uint32_t bar, int c0, int c1, int c2) {
  asm volatile("cp.async.bulk.tensor.3d.shared::cluster.global.mbarrier::complete_tx::bytes [%0], [%1, {%3, %4, %5}], [%2];" ::"r"(dst), "l"(m), "r"(bar), "r"(c0), "r"(c1), "r"(c2) : "memory");
}
__device__ __forceinline__ void tma4d(uint32_t dst, const CUtensorMap* m, uint32_t bar, int c0, int c1, int c2, int c3) {
  asm volatile("cp.async.bulk.tensor.4d.shared::cluster.global.mbarrier::complete_tx::bytes [%0], [%1, {%3, %4, %5, %6}], [%2];" ::"r"(dst), "l"(m), "r"(bar), "r"(c0), "r"(c1), "r"(c2), "r"(c3) : "memory");
}
__device__ __forceinline__ void wg_fence() { asm volatile("wgmma.fence.sync.aligned;" ::: "memory"); }
__device__ __forceinline__ void wg_commit() { asm volatile("wgmma.commit_group.sync.aligned;" ::: "memory"); }
template <int N> __device__ __forceinline__ void wg_wait() { asm volatile("wgmma.wait_group.sync.aligned %0;" ::"n"(N) : "memory"); }
template <int O, int N, int NN> __device__ __forceinline__ void fence_regs(float (&d)[NN]) {
#pragma unroll
  for (int i = 0; i < N; i++) asm volatile("" : "+f"(d[O + i])::"memory");
}
__device__ __forceinline__ uint32_t pack_bf16(float lo, float hi) {
  uint32_t r; asm("cvt.rn.bf16x2.f32 %0, %1, %2;" : "=r"(r) : "f"(hi), "f"(lo)); return r;
}
__device__ __forceinline__ uint32_t pack_pin(float lo, float hi) {
  uint32_t r; asm volatile("cvt.rn.bf16x2.f32 %0, %1, %2;" : "=r"(r) : "f"(hi), "f"(lo) : "memory"); return r;
}
__device__ __forceinline__ float bf_lo(uint32_t u) { return __uint_as_float(u << 16); }
__device__ __forceinline__ float bf_hi(uint32_t u) { return __uint_as_float(u & 0xffff0000u); }

__device__ __forceinline__ uint64_t d128(uint32_t lo) { uint64_t d; asm("mov.b64 %0, {%1, 0x40000040};" : "=l"(d) : "r"(lo)); return d; }
__device__ __forceinline__ uint64_t d64(uint32_t lo) { uint64_t d; asm("mov.b64 %0, {%1, 0x80000020};" : "=l"(d) : "r"(lo)); return d; }
template<int O,int TB,int ACC,int NN> __device__ __forceinline__ void mma_ss64(float (&d)[NN], uint64_t da, uint64_t db, int sd = 0){
  if constexpr (ACC == 1) asm volatile("wgmma.mma_async.sync.aligned.m64n64k16.f32.bf16.bf16 {%0,%1,%2,%3,%4,%5,%6,%7,%8,%9,%10,%11,%12,%13,%14,%15,%16,%17,%18,%19,%20,%21,%22,%23,%24,%25,%26,%27,%28,%29,%30,%31}, %32, %33, 1, 1, 1, %35, %34;"
   : "+f"(d[O+0]), "+f"(d[O+1]), "+f"(d[O+2]), "+f"(d[O+3]), "+f"(d[O+4]), "+f"(d[O+5]), "+f"(d[O+6]), "+f"(d[O+7]), "+f"(d[O+8]), "+f"(d[O+9]), "+f"(d[O+10]), "+f"(d[O+11]), "+f"(d[O+12]), "+f"(d[O+13]), "+f"(d[O+14]), "+f"(d[O+15]), "+f"(d[O+16]), "+f"(d[O+17]), "+f"(d[O+18]), "+f"(d[O+19]), "+f"(d[O+20]), "+f"(d[O+21]), "+f"(d[O+22]), "+f"(d[O+23]), "+f"(d[O+24]), "+f"(d[O+25]), "+f"(d[O+26]), "+f"(d[O+27]), "+f"(d[O+28]), "+f"(d[O+29]), "+f"(d[O+30]), "+f"(d[O+31])
   : "l"(da), "l"(db), "n"(TB & 1), "n"(TB >> 1));
  else if constexpr (ACC == 0) asm volatile("wgmma.mma_async.sync.aligned.m64n64k16.f32.bf16.bf16 {%0,%1,%2,%3,%4,%5,%6,%7,%8,%9,%10,%11,%12,%13,%14,%15,%16,%17,%18,%19,%20,%21,%22,%23,%24,%25,%26,%27,%28,%29,%30,%31}, %32, %33, 0, 1, 1, %35, %34;"
   : "=f"(d[O+0]), "=f"(d[O+1]), "=f"(d[O+2]), "=f"(d[O+3]), "=f"(d[O+4]), "=f"(d[O+5]), "=f"(d[O+6]), "=f"(d[O+7]), "=f"(d[O+8]), "=f"(d[O+9]), "=f"(d[O+10]), "=f"(d[O+11]), "=f"(d[O+12]), "=f"(d[O+13]), "=f"(d[O+14]), "=f"(d[O+15]), "=f"(d[O+16]), "=f"(d[O+17]), "=f"(d[O+18]), "=f"(d[O+19]), "=f"(d[O+20]), "=f"(d[O+21]), "=f"(d[O+22]), "=f"(d[O+23]), "=f"(d[O+24]), "=f"(d[O+25]), "=f"(d[O+26]), "=f"(d[O+27]), "=f"(d[O+28]), "=f"(d[O+29]), "=f"(d[O+30]), "=f"(d[O+31])
   : "l"(da), "l"(db), "n"(TB & 1), "n"(TB >> 1));
  else asm volatile("{\n.reg .pred p;\nsetp.ne.b32 p, %36, 0;\nwgmma.mma_async.sync.aligned.m64n64k16.f32.bf16.bf16 {%0,%1,%2,%3,%4,%5,%6,%7,%8,%9,%10,%11,%12,%13,%14,%15,%16,%17,%18,%19,%20,%21,%22,%23,%24,%25,%26,%27,%28,%29,%30,%31}, %32, %33, p, 1, 1, %35, %34;\n}"
   : "+f"(d[O+0]), "+f"(d[O+1]), "+f"(d[O+2]), "+f"(d[O+3]), "+f"(d[O+4]), "+f"(d[O+5]), "+f"(d[O+6]), "+f"(d[O+7]), "+f"(d[O+8]), "+f"(d[O+9]), "+f"(d[O+10]), "+f"(d[O+11]), "+f"(d[O+12]), "+f"(d[O+13]), "+f"(d[O+14]), "+f"(d[O+15]), "+f"(d[O+16]), "+f"(d[O+17]), "+f"(d[O+18]), "+f"(d[O+19]), "+f"(d[O+20]), "+f"(d[O+21]), "+f"(d[O+22]), "+f"(d[O+23]), "+f"(d[O+24]), "+f"(d[O+25]), "+f"(d[O+26]), "+f"(d[O+27]), "+f"(d[O+28]), "+f"(d[O+29]), "+f"(d[O+30]), "+f"(d[O+31])
   : "l"(da), "l"(db), "n"(TB & 1), "n"(TB >> 1), "r"(sd));
}
template<int O,int TB,int ACC,int NN> __device__ __forceinline__ void mma_rs64(float (&d)[NN], uint32_t a0, uint32_t a1, uint32_t a2, uint32_t a3, uint64_t db, int sd = 0){
  if constexpr (ACC == 1) asm volatile("wgmma.mma_async.sync.aligned.m64n64k16.f32.bf16.bf16 {%0,%1,%2,%3,%4,%5,%6,%7,%8,%9,%10,%11,%12,%13,%14,%15,%16,%17,%18,%19,%20,%21,%22,%23,%24,%25,%26,%27,%28,%29,%30,%31}, {%32,%33,%34,%35}, %36, 1, 1, 1, %37;"
   : "+f"(d[O+0]), "+f"(d[O+1]), "+f"(d[O+2]), "+f"(d[O+3]), "+f"(d[O+4]), "+f"(d[O+5]), "+f"(d[O+6]), "+f"(d[O+7]), "+f"(d[O+8]), "+f"(d[O+9]), "+f"(d[O+10]), "+f"(d[O+11]), "+f"(d[O+12]), "+f"(d[O+13]), "+f"(d[O+14]), "+f"(d[O+15]), "+f"(d[O+16]), "+f"(d[O+17]), "+f"(d[O+18]), "+f"(d[O+19]), "+f"(d[O+20]), "+f"(d[O+21]), "+f"(d[O+22]), "+f"(d[O+23]), "+f"(d[O+24]), "+f"(d[O+25]), "+f"(d[O+26]), "+f"(d[O+27]), "+f"(d[O+28]), "+f"(d[O+29]), "+f"(d[O+30]), "+f"(d[O+31])
   : "r"(a0), "r"(a1), "r"(a2), "r"(a3), "l"(db), "n"(TB));
  else if constexpr (ACC == 0) asm volatile("wgmma.mma_async.sync.aligned.m64n64k16.f32.bf16.bf16 {%0,%1,%2,%3,%4,%5,%6,%7,%8,%9,%10,%11,%12,%13,%14,%15,%16,%17,%18,%19,%20,%21,%22,%23,%24,%25,%26,%27,%28,%29,%30,%31}, {%32,%33,%34,%35}, %36, 0, 1, 1, %37;"
   : "=f"(d[O+0]), "=f"(d[O+1]), "=f"(d[O+2]), "=f"(d[O+3]), "=f"(d[O+4]), "=f"(d[O+5]), "=f"(d[O+6]), "=f"(d[O+7]), "=f"(d[O+8]), "=f"(d[O+9]), "=f"(d[O+10]), "=f"(d[O+11]), "=f"(d[O+12]), "=f"(d[O+13]), "=f"(d[O+14]), "=f"(d[O+15]), "=f"(d[O+16]), "=f"(d[O+17]), "=f"(d[O+18]), "=f"(d[O+19]), "=f"(d[O+20]), "=f"(d[O+21]), "=f"(d[O+22]), "=f"(d[O+23]), "=f"(d[O+24]), "=f"(d[O+25]), "=f"(d[O+26]), "=f"(d[O+27]), "=f"(d[O+28]), "=f"(d[O+29]), "=f"(d[O+30]), "=f"(d[O+31])
   : "r"(a0), "r"(a1), "r"(a2), "r"(a3), "l"(db), "n"(TB));
  else asm volatile("{\n.reg .pred p;\nsetp.ne.b32 p, %38, 0;\nwgmma.mma_async.sync.aligned.m64n64k16.f32.bf16.bf16 {%0,%1,%2,%3,%4,%5,%6,%7,%8,%9,%10,%11,%12,%13,%14,%15,%16,%17,%18,%19,%20,%21,%22,%23,%24,%25,%26,%27,%28,%29,%30,%31}, {%32,%33,%34,%35}, %36, p, 1, 1, %37;\n}"
   : "+f"(d[O+0]), "+f"(d[O+1]), "+f"(d[O+2]), "+f"(d[O+3]), "+f"(d[O+4]), "+f"(d[O+5]), "+f"(d[O+6]), "+f"(d[O+7]), "+f"(d[O+8]), "+f"(d[O+9]), "+f"(d[O+10]), "+f"(d[O+11]), "+f"(d[O+12]), "+f"(d[O+13]), "+f"(d[O+14]), "+f"(d[O+15]), "+f"(d[O+16]), "+f"(d[O+17]), "+f"(d[O+18]), "+f"(d[O+19]), "+f"(d[O+20]), "+f"(d[O+21]), "+f"(d[O+22]), "+f"(d[O+23]), "+f"(d[O+24]), "+f"(d[O+25]), "+f"(d[O+26]), "+f"(d[O+27]), "+f"(d[O+28]), "+f"(d[O+29]), "+f"(d[O+30]), "+f"(d[O+31])
   : "r"(a0), "r"(a1), "r"(a2), "r"(a3), "l"(db), "n"(TB), "r"(sd));
}
template<int O,int TB,int ACC,int NN> __device__ __forceinline__ void mma_ss128(float (&d)[NN], uint64_t da, uint64_t db, int sd = 0){
  if constexpr (ACC == 1) asm volatile("wgmma.mma_async.sync.aligned.m64n128k16.f32.bf16.bf16 {%0,%1,%2,%3,%4,%5,%6,%7,%8,%9,%10,%11,%12,%13,%14,%15,%16,%17,%18,%19,%20,%21,%22,%23,%24,%25,%26,%27,%28,%29,%30,%31,%32,%33,%34,%35,%36,%37,%38,%39,%40,%41,%42,%43,%44,%45,%46,%47,%48,%49,%50,%51,%52,%53,%54,%55,%56,%57,%58,%59,%60,%61,%62,%63}, %64, %65, 1, 1, 1, %67, %66;"
   : "+f"(d[O+0]), "+f"(d[O+1]), "+f"(d[O+2]), "+f"(d[O+3]), "+f"(d[O+4]), "+f"(d[O+5]), "+f"(d[O+6]), "+f"(d[O+7]), "+f"(d[O+8]), "+f"(d[O+9]), "+f"(d[O+10]), "+f"(d[O+11]), "+f"(d[O+12]), "+f"(d[O+13]), "+f"(d[O+14]), "+f"(d[O+15]), "+f"(d[O+16]), "+f"(d[O+17]), "+f"(d[O+18]), "+f"(d[O+19]), "+f"(d[O+20]), "+f"(d[O+21]), "+f"(d[O+22]), "+f"(d[O+23]), "+f"(d[O+24]), "+f"(d[O+25]), "+f"(d[O+26]), "+f"(d[O+27]), "+f"(d[O+28]), "+f"(d[O+29]), "+f"(d[O+30]), "+f"(d[O+31]), "+f"(d[O+32]), "+f"(d[O+33]), "+f"(d[O+34]), "+f"(d[O+35]), "+f"(d[O+36]), "+f"(d[O+37]), "+f"(d[O+38]), "+f"(d[O+39]), "+f"(d[O+40]), "+f"(d[O+41]), "+f"(d[O+42]), "+f"(d[O+43]), "+f"(d[O+44]), "+f"(d[O+45]), "+f"(d[O+46]), "+f"(d[O+47]), "+f"(d[O+48]), "+f"(d[O+49]), "+f"(d[O+50]), "+f"(d[O+51]), "+f"(d[O+52]), "+f"(d[O+53]), "+f"(d[O+54]), "+f"(d[O+55]), "+f"(d[O+56]), "+f"(d[O+57]), "+f"(d[O+58]), "+f"(d[O+59]), "+f"(d[O+60]), "+f"(d[O+61]), "+f"(d[O+62]), "+f"(d[O+63])
   : "l"(da), "l"(db), "n"(TB & 1), "n"(TB >> 1));
  else if constexpr (ACC == 0) asm volatile("wgmma.mma_async.sync.aligned.m64n128k16.f32.bf16.bf16 {%0,%1,%2,%3,%4,%5,%6,%7,%8,%9,%10,%11,%12,%13,%14,%15,%16,%17,%18,%19,%20,%21,%22,%23,%24,%25,%26,%27,%28,%29,%30,%31,%32,%33,%34,%35,%36,%37,%38,%39,%40,%41,%42,%43,%44,%45,%46,%47,%48,%49,%50,%51,%52,%53,%54,%55,%56,%57,%58,%59,%60,%61,%62,%63}, %64, %65, 0, 1, 1, %67, %66;"
   : "=f"(d[O+0]), "=f"(d[O+1]), "=f"(d[O+2]), "=f"(d[O+3]), "=f"(d[O+4]), "=f"(d[O+5]), "=f"(d[O+6]), "=f"(d[O+7]), "=f"(d[O+8]), "=f"(d[O+9]), "=f"(d[O+10]), "=f"(d[O+11]), "=f"(d[O+12]), "=f"(d[O+13]), "=f"(d[O+14]), "=f"(d[O+15]), "=f"(d[O+16]), "=f"(d[O+17]), "=f"(d[O+18]), "=f"(d[O+19]), "=f"(d[O+20]), "=f"(d[O+21]), "=f"(d[O+22]), "=f"(d[O+23]), "=f"(d[O+24]), "=f"(d[O+25]), "=f"(d[O+26]), "=f"(d[O+27]), "=f"(d[O+28]), "=f"(d[O+29]), "=f"(d[O+30]), "=f"(d[O+31]), "=f"(d[O+32]), "=f"(d[O+33]), "=f"(d[O+34]), "=f"(d[O+35]), "=f"(d[O+36]), "=f"(d[O+37]), "=f"(d[O+38]), "=f"(d[O+39]), "=f"(d[O+40]), "=f"(d[O+41]), "=f"(d[O+42]), "=f"(d[O+43]), "=f"(d[O+44]), "=f"(d[O+45]), "=f"(d[O+46]), "=f"(d[O+47]), "=f"(d[O+48]), "=f"(d[O+49]), "=f"(d[O+50]), "=f"(d[O+51]), "=f"(d[O+52]), "=f"(d[O+53]), "=f"(d[O+54]), "=f"(d[O+55]), "=f"(d[O+56]), "=f"(d[O+57]), "=f"(d[O+58]), "=f"(d[O+59]), "=f"(d[O+60]), "=f"(d[O+61]), "=f"(d[O+62]), "=f"(d[O+63])
   : "l"(da), "l"(db), "n"(TB & 1), "n"(TB >> 1));
  else asm volatile("{\n.reg .pred p;\nsetp.ne.b32 p, %68, 0;\nwgmma.mma_async.sync.aligned.m64n128k16.f32.bf16.bf16 {%0,%1,%2,%3,%4,%5,%6,%7,%8,%9,%10,%11,%12,%13,%14,%15,%16,%17,%18,%19,%20,%21,%22,%23,%24,%25,%26,%27,%28,%29,%30,%31,%32,%33,%34,%35,%36,%37,%38,%39,%40,%41,%42,%43,%44,%45,%46,%47,%48,%49,%50,%51,%52,%53,%54,%55,%56,%57,%58,%59,%60,%61,%62,%63}, %64, %65, p, 1, 1, %67, %66;\n}"
   : "+f"(d[O+0]), "+f"(d[O+1]), "+f"(d[O+2]), "+f"(d[O+3]), "+f"(d[O+4]), "+f"(d[O+5]), "+f"(d[O+6]), "+f"(d[O+7]), "+f"(d[O+8]), "+f"(d[O+9]), "+f"(d[O+10]), "+f"(d[O+11]), "+f"(d[O+12]), "+f"(d[O+13]), "+f"(d[O+14]), "+f"(d[O+15]), "+f"(d[O+16]), "+f"(d[O+17]), "+f"(d[O+18]), "+f"(d[O+19]), "+f"(d[O+20]), "+f"(d[O+21]), "+f"(d[O+22]), "+f"(d[O+23]), "+f"(d[O+24]), "+f"(d[O+25]), "+f"(d[O+26]), "+f"(d[O+27]), "+f"(d[O+28]), "+f"(d[O+29]), "+f"(d[O+30]), "+f"(d[O+31]), "+f"(d[O+32]), "+f"(d[O+33]), "+f"(d[O+34]), "+f"(d[O+35]), "+f"(d[O+36]), "+f"(d[O+37]), "+f"(d[O+38]), "+f"(d[O+39]), "+f"(d[O+40]), "+f"(d[O+41]), "+f"(d[O+42]), "+f"(d[O+43]), "+f"(d[O+44]), "+f"(d[O+45]), "+f"(d[O+46]), "+f"(d[O+47]), "+f"(d[O+48]), "+f"(d[O+49]), "+f"(d[O+50]), "+f"(d[O+51]), "+f"(d[O+52]), "+f"(d[O+53]), "+f"(d[O+54]), "+f"(d[O+55]), "+f"(d[O+56]), "+f"(d[O+57]), "+f"(d[O+58]), "+f"(d[O+59]), "+f"(d[O+60]), "+f"(d[O+61]), "+f"(d[O+62]), "+f"(d[O+63])
   : "l"(da), "l"(db), "n"(TB & 1), "n"(TB >> 1), "r"(sd));
}
template<int O,int TB,int ACC,int NN> __device__ __forceinline__ void mma_rs128(float (&d)[NN], uint32_t a0, uint32_t a1, uint32_t a2, uint32_t a3, uint64_t db, int sd = 0){
  if constexpr (ACC == 1) asm volatile("wgmma.mma_async.sync.aligned.m64n128k16.f32.bf16.bf16 {%0,%1,%2,%3,%4,%5,%6,%7,%8,%9,%10,%11,%12,%13,%14,%15,%16,%17,%18,%19,%20,%21,%22,%23,%24,%25,%26,%27,%28,%29,%30,%31,%32,%33,%34,%35,%36,%37,%38,%39,%40,%41,%42,%43,%44,%45,%46,%47,%48,%49,%50,%51,%52,%53,%54,%55,%56,%57,%58,%59,%60,%61,%62,%63}, {%64,%65,%66,%67}, %68, 1, 1, 1, %69;"
   : "+f"(d[O+0]), "+f"(d[O+1]), "+f"(d[O+2]), "+f"(d[O+3]), "+f"(d[O+4]), "+f"(d[O+5]), "+f"(d[O+6]), "+f"(d[O+7]), "+f"(d[O+8]), "+f"(d[O+9]), "+f"(d[O+10]), "+f"(d[O+11]), "+f"(d[O+12]), "+f"(d[O+13]), "+f"(d[O+14]), "+f"(d[O+15]), "+f"(d[O+16]), "+f"(d[O+17]), "+f"(d[O+18]), "+f"(d[O+19]), "+f"(d[O+20]), "+f"(d[O+21]), "+f"(d[O+22]), "+f"(d[O+23]), "+f"(d[O+24]), "+f"(d[O+25]), "+f"(d[O+26]), "+f"(d[O+27]), "+f"(d[O+28]), "+f"(d[O+29]), "+f"(d[O+30]), "+f"(d[O+31]), "+f"(d[O+32]), "+f"(d[O+33]), "+f"(d[O+34]), "+f"(d[O+35]), "+f"(d[O+36]), "+f"(d[O+37]), "+f"(d[O+38]), "+f"(d[O+39]), "+f"(d[O+40]), "+f"(d[O+41]), "+f"(d[O+42]), "+f"(d[O+43]), "+f"(d[O+44]), "+f"(d[O+45]), "+f"(d[O+46]), "+f"(d[O+47]), "+f"(d[O+48]), "+f"(d[O+49]), "+f"(d[O+50]), "+f"(d[O+51]), "+f"(d[O+52]), "+f"(d[O+53]), "+f"(d[O+54]), "+f"(d[O+55]), "+f"(d[O+56]), "+f"(d[O+57]), "+f"(d[O+58]), "+f"(d[O+59]), "+f"(d[O+60]), "+f"(d[O+61]), "+f"(d[O+62]), "+f"(d[O+63])
   : "r"(a0), "r"(a1), "r"(a2), "r"(a3), "l"(db), "n"(TB));
  else if constexpr (ACC == 0) asm volatile("wgmma.mma_async.sync.aligned.m64n128k16.f32.bf16.bf16 {%0,%1,%2,%3,%4,%5,%6,%7,%8,%9,%10,%11,%12,%13,%14,%15,%16,%17,%18,%19,%20,%21,%22,%23,%24,%25,%26,%27,%28,%29,%30,%31,%32,%33,%34,%35,%36,%37,%38,%39,%40,%41,%42,%43,%44,%45,%46,%47,%48,%49,%50,%51,%52,%53,%54,%55,%56,%57,%58,%59,%60,%61,%62,%63}, {%64,%65,%66,%67}, %68, 0, 1, 1, %69;"
   : "=f"(d[O+0]), "=f"(d[O+1]), "=f"(d[O+2]), "=f"(d[O+3]), "=f"(d[O+4]), "=f"(d[O+5]), "=f"(d[O+6]), "=f"(d[O+7]), "=f"(d[O+8]), "=f"(d[O+9]), "=f"(d[O+10]), "=f"(d[O+11]), "=f"(d[O+12]), "=f"(d[O+13]), "=f"(d[O+14]), "=f"(d[O+15]), "=f"(d[O+16]), "=f"(d[O+17]), "=f"(d[O+18]), "=f"(d[O+19]), "=f"(d[O+20]), "=f"(d[O+21]), "=f"(d[O+22]), "=f"(d[O+23]), "=f"(d[O+24]), "=f"(d[O+25]), "=f"(d[O+26]), "=f"(d[O+27]), "=f"(d[O+28]), "=f"(d[O+29]), "=f"(d[O+30]), "=f"(d[O+31]), "=f"(d[O+32]), "=f"(d[O+33]), "=f"(d[O+34]), "=f"(d[O+35]), "=f"(d[O+36]), "=f"(d[O+37]), "=f"(d[O+38]), "=f"(d[O+39]), "=f"(d[O+40]), "=f"(d[O+41]), "=f"(d[O+42]), "=f"(d[O+43]), "=f"(d[O+44]), "=f"(d[O+45]), "=f"(d[O+46]), "=f"(d[O+47]), "=f"(d[O+48]), "=f"(d[O+49]), "=f"(d[O+50]), "=f"(d[O+51]), "=f"(d[O+52]), "=f"(d[O+53]), "=f"(d[O+54]), "=f"(d[O+55]), "=f"(d[O+56]), "=f"(d[O+57]), "=f"(d[O+58]), "=f"(d[O+59]), "=f"(d[O+60]), "=f"(d[O+61]), "=f"(d[O+62]), "=f"(d[O+63])
   : "r"(a0), "r"(a1), "r"(a2), "r"(a3), "l"(db), "n"(TB));
  else asm volatile("{\n.reg .pred p;\nsetp.ne.b32 p, %70, 0;\nwgmma.mma_async.sync.aligned.m64n128k16.f32.bf16.bf16 {%0,%1,%2,%3,%4,%5,%6,%7,%8,%9,%10,%11,%12,%13,%14,%15,%16,%17,%18,%19,%20,%21,%22,%23,%24,%25,%26,%27,%28,%29,%30,%31,%32,%33,%34,%35,%36,%37,%38,%39,%40,%41,%42,%43,%44,%45,%46,%47,%48,%49,%50,%51,%52,%53,%54,%55,%56,%57,%58,%59,%60,%61,%62,%63}, {%64,%65,%66,%67}, %68, p, 1, 1, %69;\n}"
   : "+f"(d[O+0]), "+f"(d[O+1]), "+f"(d[O+2]), "+f"(d[O+3]), "+f"(d[O+4]), "+f"(d[O+5]), "+f"(d[O+6]), "+f"(d[O+7]), "+f"(d[O+8]), "+f"(d[O+9]), "+f"(d[O+10]), "+f"(d[O+11]), "+f"(d[O+12]), "+f"(d[O+13]), "+f"(d[O+14]), "+f"(d[O+15]), "+f"(d[O+16]), "+f"(d[O+17]), "+f"(d[O+18]), "+f"(d[O+19]), "+f"(d[O+20]), "+f"(d[O+21]), "+f"(d[O+22]), "+f"(d[O+23]), "+f"(d[O+24]), "+f"(d[O+25]), "+f"(d[O+26]), "+f"(d[O+27]), "+f"(d[O+28]), "+f"(d[O+29]), "+f"(d[O+30]), "+f"(d[O+31]), "+f"(d[O+32]), "+f"(d[O+33]), "+f"(d[O+34]), "+f"(d[O+35]), "+f"(d[O+36]), "+f"(d[O+37]), "+f"(d[O+38]), "+f"(d[O+39]), "+f"(d[O+40]), "+f"(d[O+41]), "+f"(d[O+42]), "+f"(d[O+43]), "+f"(d[O+44]), "+f"(d[O+45]), "+f"(d[O+46]), "+f"(d[O+47]), "+f"(d[O+48]), "+f"(d[O+49]), "+f"(d[O+50]), "+f"(d[O+51]), "+f"(d[O+52]), "+f"(d[O+53]), "+f"(d[O+54]), "+f"(d[O+55]), "+f"(d[O+56]), "+f"(d[O+57]), "+f"(d[O+58]), "+f"(d[O+59]), "+f"(d[O+60]), "+f"(d[O+61]), "+f"(d[O+62]), "+f"(d[O+63])
   : "r"(a0), "r"(a1), "r"(a2), "r"(a3), "l"(db), "n"(TB), "r"(sd));
}

#define NEARLY 0
#define XAHEAD 3
#define HM 2
#define WBATCH 1
#define SPACE 0
#define WPF 0
#define WAFTER 7
#define WPACE 0
#define GATE_AT 4
#define TPACE 40
#define PFMODE 0
#define MAPMODE 0
template <int V> struct IC { static constexpr int value = V; };
struct Maps { CUtensorMap x, ft, g64, u64, e, wr, wi, xs, ts, t, g32, u32, d224; };

constexpr int NCTA = 130;
constexpr int U = 16384;
constexpr int TB = 36864;
constexpr int OFF_RING = 8 * U, OFF_Z = 9 * U, OFF_XB = 12 * U, OFF_T = 13 * U, OFF_D = OFF_T;
constexpr int OFF_BAR = 14 * U, OFF_SP = OFF_BAR + 512, OFF_G = OFF_SP + 1024 + 128;
constexpr int SMEM_BYTES = OFF_G + 512;
constexpr int B_FX = 0, B_FA = 8, B_FT = 12, B_Z = 16, B_W = 20, B_HX = 21, B_TL = 22, B_HP = 23, B_WR = 26, B_E0 = 30;
constexpr int B_EA = 31, B_ET = 35, B_PZ = 39, B_RDY = 41, B_FE = 42;
constexpr int B_T = 46, B_XS = 47, B_G = 49, NBAR = 50;
__host__ __device__ constexpr int rslot(int n) { return n & 3; }
__host__ __device__ constexpr int rpar(int n) { return (n >> 2) & 1; }

__global__ void __cluster_dims__(2, 1, 1) __launch_bounds__(512, 1)
fused_kernel(const __grid_constant__ Maps maps, const __nv_bfloat16* __restrict__ x, const __nv_bfloat16* __restrict__ w_r,
             const __nv_bfloat16* __restrict__ w_i, const __nv_bfloat16* __restrict__ gate_w, __nv_bfloat16* __restrict__ out) {
  extern __shared__ __align__(1024) uint8_t smem[];
  const uint32_t sb = smem_u32(smem);
  const uint32_t bars = sb + OFF_BAR;
  const int tid = threadIdx.x, lane = tid & 31;
  const int warp = __shfl_sync(0xffffffffu, tid >> 5, 0);
  const bool helper = blockIdx.x >= 128;
  const int cl = (blockIdx.x >> 1) & 63, rank = blockIdx.x & 1;
  const int q4 = cl & 3, rb = cl >> 2;
  const int j = 2 * q4 + rank;
  const int f_full = 448 * q4 + (rank ? 256 : 0);
  const int f_half = 448 * q4 + (rank ? 224 : 192);
  const int kg = 2 * j + (rb >> 3), tn = rb & 7;

  if (tid == 64) { PROF_EV(0); PROF_CK(40); }
  if (warp < 8) {
    asm volatile("barrier.cluster.arrive.relaxed.aligned;" ::: "memory");
    asm volatile("setmaxnreg.inc.sync.aligned.u32 192;");
    if (!helper) {
      const int wg = warp >> 2, w = warp & 3, g = lane >> 2;
      const bool elect = (tid & 127) == 0;
      float cX[32], cA[64], cB[64], cC[64], ci[64], ct[64];
      const int zero = blockIdx.x >> 16;
      uint32_t h[56], yf[16];
      const uint32_t d0 = (sb & 0x3FFFF) >> 4;
      const uint32_t dK = d0 | (1u << 16), dN = d0 | (512u << 16);
      const uint32_t dX = dK + wg * 512;
      constexpr uint32_t RING = OFF_RING >> 4;
      auto waitA = [&](int n) { mbar_wait(bars + 8 * (B_FA + rslot(n)), rpar(n)); };
      auto freeA = [&](int n) { mbar_arrive_if(elect, bars + 8 * (B_EA + rslot(n))); };
      auto nop = [] {};

      asm volatile("bar.sync 0, 384;" ::: "memory");
#pragma unroll 1
      for (int i = 0; i < 4; i++) {
        const uint64_t dx = d128(dX + i * 2048), df = d128(dK + (OFF_XB >> 4) + (i & 1) * 1024);
        mbar_wait(bars + 8 * (B_FX + 2 * i), 0);
        wg_fence();
        mma_ss64<0, 0, 2>(cX, df, dx, i);
        mma_ss64<0, 0, 1>(cX, df + 2, dx + 2);
        wg_commit(); wg_wait<1>();
        mbar_arrive_if(elect && i, bars + 8 * (B_EA + rslot(i - 1)));
        mma_ss64<0, 0, 1>(cX, df + 4, dx + 4);
        mma_ss64<0, 0, 1>(cX, df + 6, dx + 6);
        if (i == 0 && tid == 0) PROF_EV(1);
        mbar_wait(bars + 8 * (B_FX + 2 * i + 1), 0);
        wg_fence();
#pragma unroll
        for (int k = 0; k < 4; k++) mma_ss64<0, 0, 1>(cX, df + (512 + k * 2), dx + (1024 + k * 2));
        wg_commit();
        waitA(i);
        wg_fence();
        const uint64_t da = d128(dX + i * 1024), db = d128(dN + RING + i * 1024);
        mma_ss128<0, 1, 2>(cA, da, db, i);
        wg_commit(); wg_wait<1>();
        mbar_arrive_if(elect, bars + 8 * (B_FE + i));
#pragma unroll
        for (int k = 1; k < 4; k++) mma_ss128<0, 1, 1>(cA, da + k * 2, db + k * 128);
        wg_commit();
      }
      fence_regs<0, 32>(cX);
#pragma unroll
      for (int e = 0; e < 16; e++) yf[e] = pack_pin(cX[2 * e], cX[2 * e + 1]);
      if (tid == 0) PROF_EV(2);
      {
        waitA(4); mbar_wait(bars + 8 * B_E0, 0);
        const uint64_t de = d128(dN + (wg ? RING : OFF_XB >> 4));
        wg_fence();
        mma_rs128<0, 1, 0>(cB, yf[0], yf[1], yf[2], yf[3], de);
        wg_commit();
        wg_wait<1>();
        freeA(3);
#pragma unroll
        for (int k = 1; k < 4; k++) mma_rs128<0, 1, 1>(cB, yf[4 * k], yf[4 * k + 1], yf[4 * k + 2], yf[4 * k + 3], de + k * 128);
        wg_commit();
      }
      bool rel = false;
      auto acquire = [&](int n) {
        rel = elect;
        if (!mbar_try(bars + 8 * (B_FA + rslot(n)), rpar(n))) { wg_wait<0>(); freeA(n - 1); rel = false; waitA(n); }
      };
      auto freeP = [&](int n) { mbar_arrive_if(rel, bars + 8 * (B_EA + rslot(n - 1))); };
      auto ffn_step = [&](auto first, auto split, float (&acc)[64], int n, int kb, auto done, auto work) {
        constexpr int SPLIT = decltype(split)::value;
        acquire(n);
        wg_fence();
        const uint64_t dx = d128(dX + kb * 1024), db = d128(dN + RING + rslot(n) * 1024);
        mma_ss128<0, 1, decltype(first)::value>(acc, dx, db, zero);
#pragma unroll
        for (int k = 1; k < SPLIT; k++) mma_ss128<0, 1, 1>(acc, dx + k * 2, db + k * 128);
        wg_commit();
        work();
        wg_wait<1>();
        freeP(n);
        done();
        if (SPLIT < 4) {
          wg_fence();
#pragma unroll
          for (int k = SPLIT; k < 4; k++) mma_ss128<0, 1, 1>(acc, dx + k * 2, db + k * 128);
          wg_commit();
        }
      };
      {
        const int s0 = 2 * rb + wg, kr = 2 * ((s0 & 1) | ((s0 & 4) >> 1));
        const int m = lane >> 3, r = lane & 7;
        const uint32_t a0 = sb + OFF_XB + wg * 8192 + (((w >> 1) * 8 + (m >> 1)) * 2 + (w & 1)) * 256 + (m & 1) * 128 + ((r ^ (kr + (m & 1))) << 4);
        ffn_step(IC<1>(), IC<4>(), cA, 5, 4, [&] { fence_regs<0, 64>(cB); }, nop);
        asm volatile("bar.sync 5, 256;" ::: "memory");
#pragma unroll
        for (int i = 0; i < 4; i++)
          stsm4t(a0 + i * 1024, pack_bf16(cB[8 * i] - cB[34 + 8 * i], cB[8 * i + 1] - cB[35 + 8 * i]),
                 pack_bf16(cB[32 + 8 * i] + cB[8 * i + 2], cB[33 + 8 * i] + cB[8 * i + 3]),
                 pack_bf16(cB[8 * i + 4] - cB[38 + 8 * i], cB[8 * i + 5] - cB[39 + 8 * i]),
                 pack_bf16(cB[36 + 8 * i] + cB[8 * i + 6], cB[37 + 8 * i] + cB[8 * i + 7]));
        if (j == 0 && w == 0) {
          const uint32_t a1 = r ? sb + OFF_SP + 1024 : sb + OFF_SP + wg * 512 + (m & 1) * 256 + (m >> 1) * 128;
#pragma unroll
          for (int n = 0; n < 8; n++)
            asm volatile("stmatrix.sync.aligned.m8n8.x4.shared.b16 [%0], {%1,%2,%3,%4};" ::"r"(a1 + ((n ^ (kr + (m >> 1))) << 4)),
                         "r"(pack_bf16(cB[4 * n], cB[4 * n + 1])), "r"(pack_bf16(cB[4 * n + 2], cB[4 * n + 3])),
                         "r"(pack_bf16(cB[32 + 4 * n], cB[33 + 4 * n])), "r"(pack_bf16(cB[34 + 4 * n], cB[35 + 4 * n])) : "memory");
        }
        ffn_step(IC<1>(), IC<2>(), cA, 6, 5, nop, [&] {
          asm volatile("fence.proxy.async.shared::cta;" ::: "memory");
          __syncwarp();
          mbar_arrive_if(lane == 0, bars + 8 * (B_XS + wg));
          if (tid == 0) PROF_EV(3);
        });
      }
#pragma unroll 1
      for (int kb = 6; kb < 8; kb++) ffn_step(IC<1>(), IC<1>(), cA, 1 + kb, kb, nop, nop);
      ffn_step(IC<2>(), IC<1>(), cB, 9, 0, [&] { fence_regs<0, 64>(cA); }, nop);
#pragma unroll 1
      for (int kb = 1; kb < 6; kb++) ffn_step(IC<1>(), IC<1>(), cB, 9 + kb, kb, nop, nop);
      mbar_wait(bars + 8 * B_G, 0);
      const uint32_t gb0 = *(const uint32_t*)(smem + OFF_G + (wg * 64 + w * 16 + g) * 4), gb1 = *(const uint32_t*)(smem + OFF_G + (wg * 64 + w * 16 + g + 8) * 4);
      const uint32_t tag = gb0 & 1;
      const float g0 = __uint_as_float(gb0 & ~1u), g1 = __uint_as_float(gb1 & ~1u);
      const float o0 = 1.0f - g0, o1 = 1.0f - g1;
      auto glu = [&](auto& acc, int half, int ho, int i0, int i1) {
#pragma unroll
        for (int i = i0; i < i1; i++) {
          const float o = (i & 1) ? o1 : o0;
          h[ho + i] = pack_pin(fmaxf(acc[2 * i], 0.f) * acc[half + 2 * i] * o, fmaxf(acc[2 * i + 1], 0.f) * acc[half + 1 + 2 * i] * o);
        }
      };
      ffn_step(IC<1>(), IC<1>(), cB, 15, 6, nop, [&] { glu(cA, 32, 0, 0, 8); });
      ffn_step(IC<1>(), IC<1>(), cB, 16, 7, nop, [&] { glu(cA, 32, 0, 8, 16); });
      ffn_step(IC<0>(), IC<1>(), cC, 17, 0, [&] { fence_regs<0, 64>(cB); }, nop);
      if (tid == 0) PROF_EV(4);
      ffn_step(IC<1>(), IC<1>(), cC, 18, 1, nop, [&] { glu(cB, 32, 16, 0, 8); });
      ffn_step(IC<1>(), IC<1>(), cC, 19, 2, nop, [&] { glu(cB, 32, 16, 8, 16); });
#pragma unroll 1
      for (int kb = 3; kb < 8; kb++) ffn_step(IC<1>(), IC<1>(), cC, 17 + kb, kb, nop, nop);
      if (tid == 0) PROF_EV(5);
      auto m_step = [&](auto first, int i, auto done, auto work) {
        acquire(25 + i);
        wg_fence();
        const uint64_t dx = d128(dX + i * 2048), dm = d64(dN + RING + rslot(25 + i) * 1024);
        mma_ss64<0, 1, decltype(first)::value>(ct, dx, dm);
        mma_ss64<0, 1, 1>(ct, dx + 2, dm + 64);
        wg_commit();
        work();
        wg_wait<1>();
        freeP(25 + i);
        done();
        wg_fence();
#pragma unroll
        for (int k = 2; k < 8; k++) mma_ss64<0, 1, 1>(ct, dx + ((k >> 2) * 1024 + (k & 3) * 2), dm + k * 64);
        wg_commit();
      };
      auto freeT = [&](int t) { mbar_arrive_if(elect, bars + 8 * (B_ET + t)); };
      m_step(IC<0>(), 0, [&] { fence_regs<0, 64>(cC); }, nop);
      m_step(IC<1>(), 1, [&] { freeT(0); }, [&] { glu(cC, 32, 32, 0, 5); });
      m_step(IC<1>(), 2, [&] { freeT(1); }, [&] { glu(cC, 32, 32, 5, 11); });
      m_step(IC<1>(), 3, [&] { freeT(2); }, [&] { glu(cC, 32, 32, 11, 16); });
      waitA(29 + wg);
      if (tid == 0) PROF_EV(6);
      mbar_wait(bars + 8 * (j == 0 ? B_T : B_TL), 0);
      if (tid == 0) PROF_EV(7);
      wg_fence();
      {
        const uint64_t dt = d128(dN + (OFF_T >> 4) + wg * 512), de = d128(dK + RING + (1 + wg) * 1024);
        mma_ss64<0, 1, 0>(ci, de, dt);
        mma_ss64<32, 1, 0>(ci, de + 512, dt);
#pragma unroll
        for (int k = 1; k < 4; k++) {
          mma_ss64<0, 1, 1>(ci, de + k * 2, dt + k * 128);
          mma_ss64<32, 1, 1>(ci, de + (512 + k * 2), dt + k * 128);
        }
        wg_commit();
        wg_wait<1>();
        freeT(3);
        fence_regs<0, 32>(ct);
        glu(ct, 16, 48, 0, 8);
      }

      auto head = [&](auto off, int t, auto first) {
        constexpr int O = decltype(off)::value;
        mbar_wait(bars + 8 * (B_FT + (t & 3)), t >> 2);
        const uint64_t db = d128(dN + (t & 3) * (TB >> 4) + rank * 256);
        wg_fence();
        mma_rs64<O, 1, decltype(first)::value>(ct, h[0], h[1], h[2], h[3], db, zero);
#pragma unroll
        for (int k = 1; k < 6; k++) mma_rs64<O, 1, 1>(ct, h[4 * k], h[4 * k + 1], h[4 * k + 2], h[4 * k + 3], db + k * 128);
        wg_commit();
        wg_wait<1>();
      };
      auto rest = [&](auto off, int t) {
        constexpr int O = decltype(off)::value;
        const uint64_t db = d128(dN + (t & 3) * (TB >> 4)), dw = db + rank * 256, dm = db + (rank ? 0 : 1536);
        wg_fence();
#pragma unroll
        for (int k = 6; k < 12; k++) mma_rs64<O, 1, 1>(ct, h[4 * k], h[4 * k + 1], h[4 * k + 2], h[4 * k + 3], dw + k * 128);
#pragma unroll
        for (int k = 0; k < 2; k++) mma_rs64<O, 1, 1>(ct, h[48 + 4 * k], h[49 + 4 * k], h[50 + 4 * k], h[51 + 4 * k], dm + k * 128);
#pragma unroll
        for (int k = 0; k < 4; k++) mma_rs64<O, 1, 1>(ct, yf[4 * k], yf[4 * k + 1], yf[4 * k + 2], yf[4 * k + 3], db + (14 + k) * 128);
        wg_commit();
      };
      const uint32_t peerZ = mapa(sb + OFF_Z + tid * 16, rank ^ 1), peerB = mapa(bars + 8 * B_Z, rank ^ 1);
      auto send = [&](auto off, int t) {
        constexpr int O = decltype(off)::value;
        fence_regs<O, 32>(ct);
        const bool grid = t >= 3 && t < 6;
        const int z = grid ? t - 3 : t == 6 ? 3 : t;
        if (grid) {
          mbar_wait(bars + 8 * (B_Z + z), 0);
#pragma unroll
          for (int i = 0; i < 4; i++) {
            const uint4 p = *(const uint4*)(smem + OFF_Z + z * U + i * 4096 + tid * 16);
            const uint32_t a[4] = {p.x, p.y, p.z, p.w};
#pragma unroll
            for (int e = 0; e < 4; e++) { ct[O + 8 * i + 2 * e] += bf_lo(a[e]); ct[O + 8 * i + 2 * e + 1] += bf_hi(a[e]); }
          }
        }
        uint32_t pk[16];
#pragma unroll
        for (int i = 0; i < 16; i++) pk[i] = pack_bf16(ct[O + 2 * i], ct[O + 2 * i + 1]);
        if (grid) {
          const int owner = rb * 8 + 2 * ((q4 + z + 1) & 3) + rank;
          uint4* dst = g_part + (size_t)(owner * 3 + z) * 1024 + tid;
#pragma unroll
          for (int i = 0; i < 4; i++) st_x4(dst + i * 256, (pk[4 * i] & ~1u) | tag, pk[4 * i + 1], pk[4 * i + 2], pk[4 * i + 3]);
          __syncwarp();
          hint_add_if(lane == 0, &g_cntP[32 * owner + z]);
        } else {
#pragma unroll
          for (int i = 0; i < 4; i++)
            asm volatile("st.async.weak.shared::cluster.mbarrier::complete_tx::bytes.v4.b32 [%0], {%1,%2,%3,%4}, [%5];" ::"r"(peerZ + z * U + i * 4096),
                         "r"(pk[4 * i]), "r"(pk[4 * i + 1]), "r"(pk[4 * i + 2]), "r"(pk[4 * i + 3]), "r"(peerB + 8 * z) : "memory");
        }
      };
      asm volatile("barrier.cluster.wait.aligned;" ::: "memory");
      head(IC<0>(), 0, IC<2>());
      if (elect) asm volatile("mbarrier.arrive.shared::cluster.b64 _, [%0];" ::"r"(mapa(bars + 8 * B_RDY, rank ^ 1)) : "memory");
      fence_regs<0, 64>(ci);
#pragma unroll
      for (int i = 0; i < 16; i++) {
        const float gg = ((i & 1) ? g1 : g0) * (2.0f / (2048.0f * 512.0f));
        if (i & 2) yf[i] = pack_pin((ci[2 * i] - ci[28 + 2 * i]) * gg, (ci[2 * i + 1] - ci[29 + 2 * i]) * gg);
        else yf[i] = pack_pin((ci[2 * i] + ci[36 + 2 * i]) * gg, (ci[2 * i + 1] + ci[37 + 2 * i]) * gg);
      }
      if (tid == 0) PROF_EV(8);
#pragma unroll 1
      for (int t = 0;; t += 2) {
        rest(IC<0>(), t);
        head(IC<32>(), t + 1, IC<2>());
        mbar_arrive_if(elect && t < 6, bars + 8 * (B_ET + t));
        if (t == 0) mbar_wait(bars + 8 * B_RDY, 0);
        send(IC<0>(), t);
        rest(IC<32>(), t + 1);
        if (t == 6) break;
        head(IC<0>(), t + 2, IC<2>());
        mbar_arrive_if(elect, bars + 8 * (B_ET + t + 1));
        send(IC<32>(), t + 1);
      }
      if (tid == 0) PROF_EV(9);
      {
        float sum[32];
        mbar_wait(bars + 8 * (B_Z + 3), 0);
#pragma unroll
        for (int i = 0; i < 4; i++) {
          const uint4 p = *(const uint4*)(smem + OFF_Z + 3 * U + i * 4096 + tid * 16);
          const uint32_t a[4] = {p.x, p.y, p.z, p.w};
#pragma unroll
          for (int e = 0; e < 4; e++) { sum[8 * i + 2 * e] = bf_lo(a[e]); sum[8 * i + 2 * e + 1] = bf_hi(a[e]); }
        }
#pragma unroll 1
        for (int z = 0; z < 3; z++) {
          mbar_wait(bars + 8 * (B_HP + z), 0);
          if (z == 2 && tid == 0) PROF_EV(24);
          uint4 pv[4];
#pragma unroll
          for (int i = 0; i < 4; i++) pv[i] = *(const uint4*)(smem + z * U + i * 4096 + tid * 16);
          const uint32_t t0 = (uint32_t)clock();
          while (__any_sync(0xffffffffu, ((pv[0].x ^ tag) | (pv[1].x ^ tag) | (pv[2].x ^ tag) | (pv[3].x ^ tag)) & 1)) {
#pragma unroll
            for (int i = 0; i < 4; i++) pv[i] = ld_x4(g_part + (size_t)((rb * 8 + j) * 3 + z) * 1024 + tid + i * 256);
            spin_guard(t0);
          }
#pragma unroll
          for (int i = 0; i < 4; i++) {
            const uint32_t a[4] = {pv[i].x & ~1u, pv[i].y, pv[i].z, pv[i].w};
#pragma unroll
            for (int e = 0; e < 4; e++) { sum[8 * i + 2 * e] += bf_lo(a[e]); sum[8 * i + 2 * e + 1] += bf_hi(a[e]); }
          }
        }
        if (tid == 0) PROF_EV(14);
        wg_wait<0>();
        fence_regs<32, 32>(ct);
#pragma unroll
        for (int i = 0; i < 32; i++) sum[i] += ct[32 + i];
        const uint32_t stg = sb + OFF_T + warp * 2048;
        const int mr = (lane & 7) + ((lane >> 3) & 1) * 8, mc = lane >> 4;
#pragma unroll
        for (int i = 0; i < 4; i++) {
          const uint32_t a = stg + mr * 128 + (((2 * i + mc) ^ (mr & 7)) << 4);
          asm volatile("stmatrix.sync.aligned.m8n8.x4.shared.b16 [%0], {%1,%2,%3,%4};" ::"r"(a), "r"(pack_bf16(sum[8 * i], sum[8 * i + 1])),
                       "r"(pack_bf16(sum[8 * i + 2], sum[8 * i + 3])), "r"(pack_bf16(sum[8 * i + 4], sum[8 * i + 5])),
                       "r"(pack_bf16(sum[8 * i + 6], sum[8 * i + 7])) : "memory");
        }
        __syncwarp();
#pragma unroll
        for (int i = 0; i < 4; i++) {
          const int r = 4 * i + (lane >> 3), c = lane & 7;
          const uint4 v = *(const uint4*)(smem + OFF_T + warp * 2048 + r * 128 + ((c ^ (r & 7)) << 4));
          *(uint4*)(out + (size_t)(2 * rb + wg + 32 * (16 * w + r)) * 512 + 64 * j + 8 * c) = v;
        }
      }
      if (tid == 0) { PROF_EV(15); PROF_CK(41); }
    }
  } else if (warp < 12) {
    asm volatile("setmaxnreg.dec.sync.aligned.u32 104;");
    asm volatile("barrier.cluster.arrive.relaxed.aligned;" ::: "memory");
    const int t = tid - 256, w = warp - 8;
    const uint32_t ep = ld_x1(&g_epoch[blockIdx.x * 8]);
    const uint32_t tag = (ep + 1) & 1;
    auto gate_rows = [&] {
      const int r = 16 * j + 4 * w + (lane >> 3);
      const uint4* px = (const uint4*)(x + (size_t)(2 * rb + (r >> 6) + 32 * (r & 63)) * 512) + (lane & 7);
      const uint4* pg = (const uint4*)gate_w + (lane & 7);
      {
        float a = 0.f;
#pragma unroll 1
        for (int i = 0; i < 8; i += 4) {
          uint4 u[4], v[4];
#pragma unroll
          for (int e = 0; e < 4; e++) { u[e] = __ldg(px + (i + e) * 8); v[e] = __ldg(pg + (i + e) * 8); }
#pragma unroll
          for (int e = 0; e < 4; e++) {
            a = fmaf(bf_lo(u[e].x), bf_lo(v[e].x), a); a = fmaf(bf_hi(u[e].x), bf_hi(v[e].x), a);
            a = fmaf(bf_lo(u[e].y), bf_lo(v[e].y), a); a = fmaf(bf_hi(u[e].y), bf_hi(v[e].y), a);
            a = fmaf(bf_lo(u[e].z), bf_lo(v[e].z), a); a = fmaf(bf_hi(u[e].z), bf_hi(v[e].z), a);
            a = fmaf(bf_lo(u[e].w), bf_lo(v[e].w), a); a = fmaf(bf_hi(u[e].w), bf_hi(v[e].w), a);
          }
        }
#pragma unroll
        for (int o = 4; o; o >>= 1) a += __shfl_xor_sync(0xffffffffu, a, o);
        if ((lane & 7) == 0)
          asm volatile("st.relaxed.gpu.global.f32 [%0], %1;" ::"l"(g_gate + rb * 128 + r), "f"(tagf(__fdividef(1.0f, 1.0f + __expf(-a)), tag)) : "memory");
        if (t == 0) PROF_EV(18);
      }
    };
    {
      const int g = lane >> 2, q = lane & 3;
      uint32_t wf[32];
      if (!helper) {
        asm volatile("bar.sync 4, 256;" ::: "memory");
        const uint32_t wa = sb + OFF_T + w * (3072 + 4) + q * 48 + g * 2;
        auto w_issue = [&](const CUtensorMap* m) {
          if (lane == 0) { mbar_expect_tx(bars + 8 * (B_WR + w), 3072); tma4d(sb + OFF_T + w * 3072, m, bars + 8 * (B_WR + w), 16 * kg, 0, 2 * w, tn); }
          __syncwarp();
        };
        mbar_wait(bars + 8 * (B_FE + 3), 0);
        if (t == 0) PROF_EV(32);
        w_issue(&maps.wr);
        gate_rows();
#pragma unroll 1
        for (int ri = 0; ri < 2; ri++) {
          mbar_wait(bars + 8 * (B_WR + w), ri);
#pragma unroll
          for (int n2 = 0; n2 < 2; n2++) {
            uint32_t v[16];
#pragma unroll
            for (int i = 0; i < 16; i++)
              asm volatile("ld.shared.u16 %0, [%1];" : "=r"(v[i]) : "r"(wa + (4 * n2 + ((i >> 1) & 3)) * 192 + (i & 1) * (1536 + 2) + (i >> 3) * 16) : "memory");
#pragma unroll
            for (int i = 0; i < 16; i++) {
              uint32_t& d = wf[(i >> 3) * 16 + 8 * n2 + (i & 7)];
              d = __byte_perm(d, v[i], 0x5432);
              asm volatile("" : "+r"(d)::"memory");
            }
          }
          __syncwarp();
          if (ri == 0) w_issue(&maps.wi);
        }
        asm volatile("bar.sync 1, 128;" ::: "memory");
        if (t == 0) PROF_EV(11);
      } else {
        asm volatile("bar.sync 4, 256;" ::: "memory");
        hint_wait(&g_cntW[0], (ep + 1) * 128u);
        const uint32_t t0 = (uint32_t)clock();
#pragma unroll 1
        for (;;) {
          uint32_t bad = 0;
#pragma unroll
          for (int i = 0; i < 32; i++) {
            const float2 v = ld_x2((const float2*)g_Wh + (i >> 4) * 2048 + 16 * w + g + 8 * (i & 1) + 64 * q + ((i >> 1) & 7) * 256);
            wf[i] = __float_as_uint(v.x); bad |= __float_as_uint(v.y) ^ tag;
          }
          if (!__any_sync(0xffffffffu, bad & 1)) break;
          spin_guard(t0);
        }
        if (t == 0) PROF_EV(11);
      }
      if (t == 0) { mbar_expect_tx(bars + 8 * B_W, 8192); bulk_load(sb + OFF_D, g_DT.v, 8192, bars + 8 * B_W); }
      if (!helper) {
        const uint32_t t0 = (uint32_t)clock();
        uint32_t v;
        do { v = ld_x1(g_gate + rb * 128 + t); spin_guard(t0); } while (__any_sync(0xffffffffu, (v ^ tag) & 1));
        *(uint32_t*)(smem + OFF_G + t * 4) = v;
        __syncwarp();
        mbar_arrive_if(lane == 0, bars + 8 * B_G);
      }
      mbar_wait(bars + 8 * B_W, 0);
      mbar_wait(bars + 8 * B_HX, 0);
      if (t == 0) PROF_EV(12);
      const uint32_t dd = (sb & 0x3FFFF) >> 4;
      const uint64_t dF = d128((dd + (OFF_D >> 4)) | (512u << 16)), dI = d128((dd + (OFF_D >> 4)) | (1u << 16)), dA = d128((dd + (OFF_XB >> 4)) | (512u << 16));
      float az[32];
      const int zero = blockIdx.x >> 16;
      uint32_t pf[32];
#pragma unroll
      for (int mt = 0; mt < 2; mt++) {
        wg_fence();
        if (mt == 0) mma_ss64<0, 3, 0>(az, dA, dF);
        else mma_ss64<0, 3, 2>(az, dA + 512, dF, zero);
#pragma unroll
        for (int k = 1; k < 4; k++) mma_ss64<0, 3, 1>(az, dA + (mt * 512 + k * 128), dF + k * 128);
        wg_commit();
        wg_wait<0>();
        fence_regs<0, 32>(az);
#pragma unroll
        for (int i = 0; i < 16; i++) {
          const float wr = bf_lo(wf[16 * mt + i]), wi = bf_hi(wf[16 * mt + i]);
          pf[16 * mt + i] = pack_pin(fmaf(az[2 * i], wr, -az[2 * i + 1] * wi), fmaf(az[2 * i], wi, az[2 * i + 1] * wr));
        }
      }
      if (t == 0) PROF_EV(16);
#pragma unroll
      for (int mt = 0; mt < 2; mt++) {
        wg_fence();
        mma_rs64<0, 0, 2>(az, pf[16 * mt], pf[16 * mt + 1], pf[16 * mt + 2], pf[16 * mt + 3], dI, mt ? (int)helper : zero);
#pragma unroll
        for (int k = 1; k < 4; k++) mma_rs64<0, 0, 1>(az, pf[16 * mt + 4 * k], pf[16 * mt + 4 * k + 1], pf[16 * mt + 4 * k + 2], pf[16 * mt + 4 * k + 3], dI + k * 2);
        wg_commit();
        wg_wait<0>();
        fence_regs<0, 32>(az);
        if (!helper) {
          const int m = lane >> 3, r = lane & 7;
          const int sl = 2 * (m >> 1) + ((r >> 1) & 1) + 4 * (r >> 2);
          const uint32_t a0 = sb + OFF_XB + (2 * w + (m & 1)) * 2048 + sl * 64 + (((mt * 2 + (r & 1)) ^ (sl >> 1)) << 4);
#pragma unroll
          for (int i = 0; i < 4; i++)
            stsm4t(a0 + i * 512, pack_bf16(az[8 * i], az[8 * i + 1]), pack_bf16(az[8 * i + 2], az[8 * i + 3]), pack_bf16(az[8 * i + 4], az[8 * i + 5]),
                   pack_bf16(az[8 * i + 6], az[8 * i + 7]));
        }
      }
      if (helper) {
#pragma unroll
        for (int i = 0; i < 16; i++) {
          const int n = i >> 1, s0 = 8 * (n >> 1) + 2 * (n & 1) + (q & 1) + 4 * (q >> 1);
          if ((n & 1) == (int)(blockIdx.x & 1)) st_u2(g_Ts + s0 * 64 + 16 * w + g + 8 * (i & 1), pack_bf16(az[2 * i], az[2 * i + 1]), tag);
        }
        __syncwarp();
        hint_add_if(lane == 0, &g_cntH[0]);
        if (t == 0) { g_epoch[blockIdx.x * 8] = ep + 1; PROF_EV(13); }
      } else {
        asm volatile("fence.proxy.async.shared::cta;" ::: "memory");
        __syncwarp();
        if (lane == 0) {
          if (t == 0) PROF_EV(17);
          if (SPACE) __nanosleep(SPACE * w);
          asm volatile("cp.async.bulk.tensor.3d.global.shared::cta.bulk_group [%0, {%2, %3, %4}], [%1];" ::"l"(&maps.ts), "r"(sb + OFF_XB + w * 4096),
                       "r"(32 * kg), "r"(0), "r"(8 * tn + 2 * w) : "memory");
          bulk_done_signal(&g_cntT[32 * j]);
          if (t == 96) PROF_EV(13);
        }
        __syncwarp();
        if (j == 0) {
          hint_wait(&g_cntH[0], (ep + 1) * 8u);
          const uint32_t t0 = (uint32_t)clock();
          float2 v;
          do { v = ld_x2((const float2*)g_Ts + 2 * rb * 64 + t); spin_guard(t0); } while (__any_sync(0xffffffffu, (__float_as_uint(v.y) ^ tag) & 1));
          mbar_wait(bars + 8 * B_TL, 0);
          const uint32_t u = __float_as_uint(v.x);
          *(uint16_t*)(smem + OFF_T + t * 128 + ((t & 7) << 4)) = (uint16_t)u;
          *(uint16_t*)(smem + OFF_T + t * 128 + (((t & 7) ^ 1) << 4)) = (uint16_t)(u >> 16);
          asm volatile("fence.proxy.async.shared::cta;" ::: "memory");
          __syncwarp();
          mbar_arrive_if(lane == 0, bars + 8 * B_T);
        }
      }
    }
  } else {
    asm volatile("setmaxnreg.dec.sync.aligned.u32 24;");
    auto xf_load = [&](int q) {
      const uint32_t fb = bars + 8 * (B_FX + q);
      mbar_expect_tx(fb, U + 8192);
      tma3d(sb + q * U, &maps.x, fb, 64 * q, 0, 2 * rb);
      if (q >= 4) mbar_wait(bars + 8 * (B_FE + ((q - 4) >> 1)), 0);
      tma2d(sb + OFF_XB + (q & 3) * 8192, &maps.ft, fb, 64 * q, 64 * j);
    };
    if (lane == 0) {
      if (warp == 14) {
#pragma unroll
        for (int i = 0; i < B_FT; i++) mbar_init(bars + 8 * i, 1);
        asm volatile("fence.proxy.async.shared::cta;" ::: "memory");
        if (!helper) {
#pragma unroll 1
          for (int n = 0; n < 2; n++) {
            const uint32_t fb = bars + 8 * (B_FA + n);
            xf_load(2 * n); xf_load(2 * n + 1);
            mbar_expect_tx(fb, U);
            tma2d(sb + OFF_RING + n * U, &maps.g64, fb, f_full, 64 * n);
            tma2d(sb + OFF_RING + n * U + 8192, &maps.u64, fb, f_full, 64 * n);
          }
        }
      } else if (warp == 15) {
#pragma unroll
        for (int i = B_FT; i < NBAR; i++) mbar_init(bars + 8 * i, i < B_EA ? 1 : i < B_T ? 2 : 4);
#pragma unroll
        for (int i = 0; i < 4; i++) mbar_expect_tx(bars + 8 * (B_Z + i), U);
        asm volatile("fence.mbarrier_init.release.cluster;" ::: "memory");
        asm volatile("fence.proxy.async.shared::cta;" ::: "memory");
      } else if (warp == 13) {
#pragma unroll
        for (int i = 1; i < 4; i++) asm volatile("prefetch.tensormap [%0];" ::"l"((const char*)&maps + i * 128) : "memory");
      }
    }
    __syncwarp();
    asm volatile("bar.arrive 0, 384;" ::: "memory");
    asm volatile("bar.arrive 4, 256;" ::: "memory");
    __syncwarp();
    asm volatile("barrier.cluster.arrive.relaxed.aligned;" ::: "memory");
    asm volatile("bar.sync 3, 128;" ::: "memory");
    if (warp == 15 && !helper) {
        mbar_wait(bars + 8 * B_FE, 0);
        const uint32_t tag = (ld_x1(&g_epoch[blockIdx.x * 8]) + 1) & 1;
        const int c = lane >> 4, jj = 16 * blockIdx.x + (lane & 15), jm = (2048 - jj) & 2047;
        const unsigned short* pr = (const unsigned short*)w_r + 256 * c;
        const unsigned short* pi = (const unsigned short*)w_i + 256 * c;
        const float wr = 0.25f * (bf_lo(__ldg(pr + jj * 257)) + bf_lo(__ldg(pr + jm * 257)));
        const float wi = 0.25f * (bf_lo(__ldg(pi + jj * 257)) - bf_lo(__ldg(pi + jm * 257)));
        st_u2(g_Wh + c * 2048 + jj, c ? pack_bf16(-wi, wr) : pack_bf16(wr, wi), tag);
        __syncwarp();
        hint_add_if(lane == 0, &g_cntW[0]);
      }
    if (lane == 0 && (!helper || warp == 15)) {
      if (warp < 14) {
        const int p = warp - 12;
#pragma unroll 1
        for (int n = 2; n < 31; n++) {
          const bool table = n == 4 || n >= 29;
          const int q = n < 4 ? n : n - 1;
          const CUtensorMap* m = table ? &maps.e : n >= 25 ? &maps.g32 + p : &maps.g64 + p;
          const int c0 = table ? 0 : n >= 25 ? f_half : f_full + 64 * (q >> 3);
          const int c1 = table ? (2 * rb + ((n & 1) ^ 1)) * 128 + 64 * p : n >= 25 ? 128 * (n - 25) : 64 * (q & 7);
          const uint32_t fb = bars + 8 * (B_FA + (n & 3)), dst = sb + OFF_RING + (n & 3) * U + p * 8192;
          if (n < 4) mbar_wait(bars + 8 * (B_FE + n - 2), 0);
          else mbar_wait(bars + 8 * (B_EA + (n & 3)), ((n >> 2) & 1) ^ 1);
          tma2d(dst, m, fb, c0, c1);
          if (p == 0) mbar_expect_tx(fb, U);
        }
      } else if (warp == 15) {
        const unsigned ep1 = ld_x1(&g_epoch[blockIdx.x * 8]) + 1;
        flag_wait(&g_cntX[helper ? 0 : 32 * j], ep1 * 16u);
        PROF_EV(22);
        mbar_expect_tx(bars + 8 * B_HX, U);
        bulk_load(sb + OFF_XB, g_X + (size_t)(helper ? 128 : kg * 8 + tn) * 8192, U, bars + 8 * B_HX);
        if (!helper) {
          flag_wait(&g_cntT[32 * j], ep1 * 64u);
          PROF_EV(23);
          mbar_expect_tx(bars + 8 * B_TL, U);
          tma3d(sb + OFF_T, &maps.t, bars + 8 * B_TL, 64 * j, 0, 2 * rb);
#pragma unroll 1
          for (int i = 0; i < 3; i++) {
            mbar_wait(bars + 8 * (B_PZ + (i >> 1)), 0);
            flag_wait(&g_cntP[32 * (rb * 8 + j) + i], ep1 * 8u);
            mbar_expect_tx(bars + 8 * (B_HP + i), U);
            bulk_load(sb + i * U, g_part + (size_t)((rb * 8 + j) * 3 + i) * 1024, U, bars + 8 * (B_HP + i));
          }
          g_epoch[blockIdx.x * 8] = ep1;
        }
      } else {
#pragma unroll 1
        for (int q = 4; q < 8; q++) xf_load(q);
        mbar_wait(bars + 8 * (B_FE + 2), 0);
        mbar_expect_tx(bars + 8 * B_E0, U);
        tma2d(sb + OFF_XB, &maps.e, bars + 8 * B_E0, 0, 2 * rb * 128);
        tma2d(sb + OFF_XB + 8192, &maps.e, bars + 8 * B_E0, 0, 2 * rb * 128 + 64);
#pragma unroll 1
        for (int h2 = 0; h2 < 2; h2++) {
          const int s0 = 2 * rb + h2, sg = (s0 & ~6) | ((s0 & 2) << 1) | ((s0 & 4) >> 1);
          mbar_wait(bars + 8 * (B_XS + h2), 0);
#pragma unroll 1
          for (int c = 0; c < 2; c++) {
            asm volatile("cp.async.bulk.tensor.4d.global.shared::cta.bulk_group [%0, {%2, %3, %4, %5}], [%1];" ::"l"(&maps.xs),
                         "r"(sb + OFF_XB + h2 * 8192 + c * 4096), "r"(0), "r"(sg), "r"(0), "r"(16 * j + 8 * c) : "memory");
            if (j == 0)
              asm volatile("cp.async.bulk.global.shared::cta.bulk_group [%0], [%1], 256;" ::"l"(g_X + 128 * 8192 + c * 4096 + sg * 128),
                           "r"(sb + OFF_SP + h2 * 512 + c * 256) : "memory");
            if (SPACE && h2 + c < 2) __nanosleep(SPACE);
          }
        }
        bulk_done_signal(&g_cntX[32 * j]);
        PROF_EV(20);
#pragma unroll 1
        for (int t = 0; t < 8; t++) {
          const int i = t < 3 ? t + 1 : t < 6 ? t - 2 : 0;
          const int col = 64 * (2 * ((q4 + i) & 3) + ((t < 3 || t == 6) ? 1 - rank : rank));
          const uint32_t fb = bars + 8 * (B_FT + (t & 3)), dst = sb + (t & 3) * TB;
          mbar_wait(bars + 8 * (B_ET + (t == 2 ? 3 : t & 3)), t >> 2);
          mbar_expect_tx(fb, TB);
          tma2d(dst, &maps.d224, fb, col, 224 * j);
          if (t < 2) mbar_wait(bars + 8 * (B_ET + t + 1), 0);
          tma2d(dst + 28672, &maps.ft, fb, col, 64 * j);
        }
      }
    }
  }
}

typedef CUresult (*EncodeFn)(CUtensorMap*, CUtensorMapDataType, cuuint32_t, void*, const cuuint64_t*, const cuuint64_t*, const cuuint32_t*,
                             const cuuint32_t*, CUtensorMapInterleave, CUtensorMapSwizzle, CUtensorMapL2promotion, CUtensorMapFloatOOBfill);

static void encode(EncodeFn f, CUtensorMap* m, const void* base, int rank, const cuuint64_t* dims, const cuuint64_t* strides, const cuuint32_t* box,
                   CUtensorMapSwizzle sw) {
  cuuint32_t es[5] = {1, 1, 1, 1, 1};
  f(m, CU_TENSOR_MAP_DATA_TYPE_BFLOAT16, rank, (void*)base, dims, strides, box, es, CU_TENSOR_MAP_INTERLEAVE_NONE, sw,
    CU_TENSOR_MAP_L2_PROMOTION_L2_128B, CU_TENSOR_MAP_FLOAT_OOB_FILL_NONE);
}

extern "C" void kernel_launch(void* const* d_in, const int* in_sizes, int n_in, void* d_out, int out_size) {
  (void)in_sizes; (void)n_in; (void)out_size;
  const __nv_bfloat16* x = (const __nv_bfloat16*)d_in[0];
  const __nv_bfloat16* w_r = (const __nv_bfloat16*)d_in[1];
  const __nv_bfloat16* w_i = (const __nv_bfloat16*)d_in[2];
  const __nv_bfloat16* Wg = (const __nv_bfloat16*)d_in[4];
  const __nv_bfloat16* Wu = (const __nv_bfloat16*)d_in[5];
  const __nv_bfloat16* Wd = (const __nv_bfloat16*)d_in[6];
  const __nv_bfloat16* gw = (const __nv_bfloat16*)d_in[7];

  void* fp = nullptr; cudaDriverEntryPointQueryResult qr;
  cudaGetDriverEntryPoint("cuTensorMapEncodeTiled", &fp, cudaEnableDefault, &qr);
  EncodeFn enc = (EncodeFn)fp;
  void *pFT, *pET, *pX, *pT;
  cudaGetSymbolAddress(&pX, g_X); cudaGetSymbolAddress(&pT, g_T);
  cudaGetSymbolAddress(&pFT, g_FT); cudaGetSymbolAddress(&pET, g_ET);

  Maps mp;
  const CUtensorMapSwizzle S128 = CU_TENSOR_MAP_SWIZZLE_128B, S64 = CU_TENSOR_MAP_SWIZZLE_64B;
  { cuuint64_t d[3] = {512, 64, 32}, s[2] = {32768, 1024}; cuuint32_t b[3] = {64, 64, 2}; encode(enc, &mp.x, x, 3, d, s, b, S128); }
  { cuuint64_t d[2] = {512, 512}, s[1] = {1024}; cuuint32_t b[2] = {64, 64}; encode(enc, &mp.ft, pFT, 2, d, s, b, S128); }
  { cuuint64_t d[4] = {128, 32, 2, 129}, s[3] = {256, 8192, 16384}; cuuint32_t b[4] = {128, 1, 2, 8}; encode(enc, &mp.xs, pX, 4, d, s, b, CU_TENSOR_MAP_SWIZZLE_NONE); }
  { cuuint64_t d[3] = {512, 32, 64}, s[2] = {65536, 1024}; cuuint32_t b[3] = {32, 32, 2}; encode(enc, &mp.ts, pT, 3, d, s, b, S64); }
  { cuuint64_t d[3] = {512, 64, 32}, s[2] = {1024, 65536}; cuuint32_t b[3] = {64, 64, 2}; encode(enc, &mp.t, pT, 3, d, s, b, S128); }
  { cuuint64_t d[2] = {64, 4096}, s[1] = {128}; cuuint32_t b[2] = {64, 64}; encode(enc, &mp.e, pET, 2, d, s, b, S128); }
  { cuuint64_t d[2] = {1792, 512}, s[1] = {3584}; cuuint32_t b[2] = {64, 64}, b2[2] = {32, 128};
    encode(enc, &mp.g64, Wg, 2, d, s, b, S128); encode(enc, &mp.u64, Wu, 2, d, s, b, S128);
    encode(enc, &mp.g32, Wg, 2, d, s, b2, S64); encode(enc, &mp.u32, Wu, 2, d, s, b2, S64); }
  { cuuint64_t d[2] = {512, 1792}, s[1] = {1024}; cuuint32_t b[2] = {64, 224}; encode(enc, &mp.d224, Wd, 2, d, s, b, S128); }
  { cuuint64_t d[4] = {264, 32, 8, 8}, s[3] = {32896, 512, 4112}; cuuint32_t b[4] = {24, 32, 2, 1};
    encode(enc, &mp.wr, w_r, 4, d, s, b, CU_TENSOR_MAP_SWIZZLE_NONE); encode(enc, &mp.wi, w_i, 4, d, s, b, CU_TENSOR_MAP_SWIZZLE_NONE); }

  cudaFuncSetAttribute(fused_kernel, cudaFuncAttributeMaxDynamicSharedMemorySize, SMEM_BYTES);
  fused_kernel<<<NCTA, 512, SMEM_BYTES>>>(mp, x, w_r, w_i, gw, (__nv_bfloat16*)d_out);
}
```

```cpp
#include <cuda_runtime.h>
#include <cuda_bf16.h>
#include <cuda.h>
#include <stdint.h>

namespace tbl {
constexpr double PI = 3.14159265358979323846264338327950288;
constexpr double sin_s(double x) { double t = x, s = x; for (int n = 1; n < 12; n++) { t *= -x * x / ((2 * n) * (2 * n + 1)); s += t; } return s; }
constexpr double cos_s(double x) { double t = 1, s = 1; for (int n = 1; n < 12; n++) { t *= -x * x / ((2 * n - 1) * (2 * n)); s += t; } return s; }
constexpr double cos2048(int m) {
  m &= 2047; if (m > 1024) m = 2048 - m;
  bool neg = false; if (m > 512) { m = 1024 - m; neg = true; }
  double v = (m <= 256) ? cos_s(2 * PI * m / 2048) : sin_s(2 * PI * (512 - m) / 2048);
  return neg ? -v : v;
}
constexpr uint16_t to_bf16(double v) {
  if (v == 0) return 0;
  uint16_t s = 0; if (v < 0) { s = 0x8000; v = -v; }
  int e = 0; while (v >= 2) { v /= 2; e++; } while (v < 1) { v *= 2; e--; }
  double m = (v - 1) * 128; int mi = (int)m; double fr = m - mi;
  if (fr > 0.5 || (fr == 0.5 && (mi & 1))) mi++;
  if (mi == 128) { mi = 0; e++; }
  return (uint16_t)(s | ((e + 127) << 7) | mi);
}
struct CosT { uint16_t v[2048]; constexpr CosT() : v() { for (int i = 0; i < 2048; i++) v[i] = to_bf16(cos2048(i)); } };
struct alignas(1024) FT {
  uint16_t v[512 * 512];
  constexpr FT() : v() {
    CosT c;
    for (int r = 0; r < 512; r++) {
      int k = (r >> 4) * 8 + (r & 7), e = (r >> 3) & 1;
      int mul = 4 * k, add = e ? 512 : 0;
      if (k == 0 && e == 1) { mul = 1024; add = 0; }
      for (int d = 0; d < 512; d++) v[r * 512 + d] = c.v[(d * mul + add) & 2047];
    }
  }
};
struct alignas(1024) ET {
  uint16_t v[2048 * 128];
  constexpr ET() : v() {
    CosT c;
    for (int s = 0; s < 2048; s++)
      for (int j = 0; j < 64; j++) {
        const int o = (s & 31) * 8192 + (s >> 5) * 64 + j;
        v[o] = c.v[(s * j) & 2047]; v[o + 4096] = c.v[(s * j + 512) & 2047];
      }
  }
};
struct alignas(1024) DT {
  uint16_t v[64 * 64];
  constexpr DT() : v() {
    CosT c;
    for (int r = 0; r < 64; r++)
      for (int n = 0; n < 64; n++) {
        const int sg = r >> 1, s0 = (sg & ~6) | ((sg & 2) << 1) | ((sg & 4) >> 1), e = r & 1, f = n & 1;
        const int m = 64 * s0 * (n >> 1) + (e == f ? 0 : e ? -512 : 512);
        v[r * 64 + (((n >> 3) ^ (r & 7)) << 3) + (n & 7)] = c.v[m & 2047];
      }
  }
};
}

__device__ constexpr tbl::FT g_FT = tbl::FT();
__device__ constexpr tbl::ET g_ET = tbl::ET();
__device__ constexpr tbl::DT g_DT = tbl::DT();

__device__ __align__(1024) uint16_t g_X[129 * 8192];
__device__ __align__(1024) uint16_t g_T[32 * 64 * 512];
__device__ __align__(1024) uint2 g_Ts[32 * 64];
__device__ __align__(1024) uint4 g_part[128 * 3 * 1024];
__device__ __align__(16) float g_gate[16 * 128];
__device__ __align__(16) uint2 g_Wh[2 * 2048];
__device__ unsigned g_epoch[132 * 8];
__device__ unsigned g_cntX[8 * 32], g_cntT[8 * 32], g_cntP[128 * 32], g_cntW[32], g_cntH[32];
#define PROF_EV(i) do {} while (0)
#define PROF_CK(i) do {} while (0)

__device__ __forceinline__ uint32_t smem_u32(const void* p) { return (uint32_t)__cvta_generic_to_shared(p); }
__device__ __forceinline__ void mbar_init(uint32_t bar, uint32_t cnt) { asm volatile("mbarrier.init.shared::cta.b64 [%0], %1;" ::"r"(bar), "r"(cnt)); }
__device__ __forceinline__ void mbar_expect_tx(uint32_t bar, uint32_t bytes) { asm volatile("mbarrier.arrive.expect_tx.shared::cta.b64 _, [%0], %1;" ::"r"(bar), "r"(bytes) : "memory"); }
__device__ __forceinline__ void mbar_arrive(uint32_t bar) { asm volatile("mbarrier.arrive.shared::cta.b64 _, [%0];" ::"r"(bar) : "memory"); }
__device__ __forceinline__ void mbar_arrive_if(bool p, uint32_t bar) {
  asm volatile("{\n.reg .pred p;\nsetp.ne.b32 p, %1, 0;\n@p mbarrier.arrive.shared::cta.b64 _, [%0];\n}" ::"r"(bar), "r"((int)p) : "memory");
}
__device__ __forceinline__ void hint_add_if(bool p, unsigned* a) {
  asm volatile("{\n.reg .pred p;\nsetp.ne.b32 p, %1, 0;\n@p red.relaxed.gpu.global.add.u32 [%0], 1;\n}" ::"l"(a), "r"((int)p) : "memory");
}
__device__ __forceinline__ bool mbar_try(uint32_t bar, uint32_t parity) {
  uint32_t ok;
  asm volatile("{\n.reg .pred p;\nmbarrier.test_wait.parity.shared::cta.b64 p, [%1], %2;\nselp.u32 %0, 1, 0, p;\n}" : "=r"(ok) : "r"(bar), "r"(parity) : "memory");
  return ok;
}
__device__ __forceinline__ void mbar_wait(uint32_t bar, uint32_t parity) {
  asm volatile(
      "{\n.reg .pred p;\n.reg .u32 n;\nmov.u32 n, 0;\n"
      "W_LOOP:\nmbarrier.try_wait.parity.shared::cta.b64 p, [%0], %1;\n@p bra W_DONE;\n"
      "add.u32 n, n, 1;\nsetp.lt.u32 p, n, 0x40000;\n@p bra W_LOOP;\ntrap;\nW_DONE:\n}" ::"r"(bar), "r"(parity) : "memory");
}
__device__ __forceinline__ void bulk_load(uint32_t dst, const void* src, uint32_t bytes, uint32_t bar) {
  asm volatile("cp.async.bulk.shared::cluster.global.mbarrier::complete_tx::bytes [%0], [%1], %2, [%3];" ::"r"(dst), "l"(src), "r"(bytes), "r"(bar) : "memory");
}
__device__ __forceinline__ void cp16(uint32_t dst, const void* src) { asm volatile("cp.async.cg.shared.global [%0], [%1], 16;" ::"r"(dst), "l"(src) : "memory"); }
__device__ __forceinline__ void spin_guard(uint32_t t0) { if ((uint32_t)clock() - t0 > (1u << 30)) __trap(); }
__device__ __forceinline__ float tagf(float v, uint32_t tag) { return __uint_as_float((__float_as_uint(v) & ~1u) | tag); }
__device__ __forceinline__ float untag(float v) { return __uint_as_float(__float_as_uint(v) & ~1u); }
__device__ __forceinline__ void st_x2(float2* p, float a, float b) { asm volatile("st.relaxed.gpu.global.v2.f32 [%0], {%1,%2};" ::"l"(p), "f"(a), "f"(b) : "memory"); }
__device__ __forceinline__ float2 ld_x2(const float2* p) { float2 v; asm volatile("ld.relaxed.gpu.global.v2.f32 {%0,%1}, [%2];" : "=f"(v.x), "=f"(v.y) : "l"(p) : "memory"); return v; }
__device__ __forceinline__ void st_u2(uint2* p, uint32_t a, uint32_t b) { asm volatile("st.relaxed.gpu.global.v2.u32 [%0], {%1,%2};" ::"l"(p), "r"(a), "r"(b) : "memory"); }
__device__ __forceinline__ void prefetch2d(const CUtensorMap* m, int c0, int c1) { asm volatile("cp.async.bulk.prefetch.tensor.2d.L2.global [%0, {%1, %2}];" ::"l"(m), "r"(c0), "r"(c1) : "memory"); }
__device__ __forceinline__ void prefetch1d(const void* p, uint32_t bytes) { asm volatile("cp.async.bulk.prefetch.L2.global [%0], %1;" ::"l"(p), "r"(bytes) : "memory"); }
__device__ __forceinline__ uint32_t ld_x1(const void* p) { uint32_t v; asm volatile("ld.relaxed.gpu.global.u32 %0, [%1];" : "=r"(v) : "l"(p) : "memory"); return v; }
__device__ __forceinline__ uint4 ld_x4(const void* p) { uint4 v; asm volatile("ld.relaxed.gpu.global.v4.u32 {%0,%1,%2,%3}, [%4];" : "=r"(v.x), "=r"(v.y), "=r"(v.z), "=r"(v.w) : "l"(p) : "memory"); return v; }
__device__ __forceinline__ void st_x4(void* p, uint32_t a, uint32_t b, uint32_t c, uint32_t d) { asm volatile("st.relaxed.gpu.global.v4.u32 [%0], {%1,%2,%3,%4};" ::"l"(p), "r"(a), "r"(b), "r"(c), "r"(d) : "memory"); }
__device__ __forceinline__ uint32_t mapa(uint32_t a, uint32_t cta) { uint32_t r; asm volatile("mapa.shared::cluster.u32 %0, %1, %2;" : "=r"(r) : "r"(a), "r"(cta)); return r; }
__device__ __forceinline__ void stsm4t(uint32_t a, uint32_t r0, uint32_t r1, uint32_t r2, uint32_t r3) {
  asm volatile("stmatrix.sync.aligned.m8n8.x4.trans.shared.b16 [%0], {%1,%2,%3,%4};" ::"r"(a), "r"(r0), "r"(r1), "r"(r2), "r"(r3) : "memory");
}
__device__ __forceinline__ void hint_add(unsigned* p) { asm volatile("red.relaxed.gpu.global.add.u32 [%0], 1;" ::"l"(p) : "memory"); }
__device__ __forceinline__ void hint_wait(const unsigned* p, unsigned target) {
  const uint32_t t0 = (uint32_t)clock();
  while ((int)(ld_x1(p) - target) < 0) spin_guard(t0);
}
__device__ __forceinline__ void bulk_done_signal(unsigned* p) {
  asm volatile("cp.async.bulk.commit_group;\ncp.async.bulk.wait_group 0;\nfence.proxy.async.global;" ::: "memory");
  hint_add(p);
}
__device__ __forceinline__ void flag_wait(const unsigned* p, unsigned target) {
  hint_wait(p, target);
  asm volatile("fence.proxy.async.global;" ::: "memory");
}
__device__ __forceinline__ void tma2d(uint32_t dst, const CUtensorMap* m, uint32_t bar, int c0, int c1) {
  asm volatile("cp.async.bulk.tensor.2d.shared::cluster.global.mbarrier::complete_tx::bytes [%0], [%1, {%3, %4}], [%2];" ::"r"(dst), "l"(m), "r"(bar), "r"(c0), "r"(c1) : "memory");
}
__device__ __forceinline__ void tma3d(uint32_t dst, const CUtensorMap* m, uint32_t bar, int c0, int c1, int c2) {
  asm volatile("cp.async.bulk.tensor.3d.shared::cluster.global.mbarrier::complete_tx::bytes [%0], [%1, {%3, %4, %5}], [%2];" ::"r"(dst), "l"(m), "r"(bar), "r"(c0), "r"(c1), "r"(c2) : "memory");
}
__device__ __forceinline__ void tma4d(uint32_t dst, const CUtensorMap* m, uint32_t bar, int c0, int c1, int c2, int c3) {
  asm volatile("cp.async.bulk.tensor.4d.shared::cluster.global.mbarrier::complete_tx::bytes [%0], [%1, {%3, %4, %5, %6}], [%2];" ::"r"(dst), "l"(m), "r"(bar), "r"(c0), "r"(c1), "r"(c2), "r"(c3) : "memory");
}
__device__ __forceinline__ void wg_fence() { asm volatile("wgmma.fence.sync.aligned;" ::: "memory"); }
__device__ __forceinline__ void wg_commit() { asm volatile("wgmma.commit_group.sync.aligned;" ::: "memory"); }
template <int N> __device__ __forceinline__ void wg_wait() { asm volatile("wgmma.wait_group.sync.aligned %0;" ::"n"(N) : "memory"); }
template <int O, int N, int NN> __device__ __forceinline__ void fence_regs(float (&d)[NN]) {
#pragma unroll
  for (int i = 0; i < N; i++) asm volatile("" : "+f"(d[O + i])::"memory");
}
__device__ __forceinline__ uint32_t pack_bf16(float lo, float hi) {
  uint32_t r; asm("cvt.rn.bf16x2.f32 %0, %1, %2;" : "=r"(r) : "f"(hi), "f"(lo)); return r;
}
__device__ __forceinline__ uint32_t pack_pin(float lo, float hi) {
  uint32_t r; asm volatile("cvt.rn.bf16x2.f32 %0, %1, %2;" : "=r"(r) : "f"(hi), "f"(lo) : "memory"); return r;
}
__device__ __forceinline__ float bf_lo(uint32_t u) { return __uint_as_float(u << 16); }
__device__ __forceinline__ float bf_hi(uint32_t u) { return __uint_as_float(u & 0xffff0000u); }

__device__ __forceinline__ uint64_t d128(uint32_t lo) { uint64_t d; asm("mov.b64 %0, {%1, 0x40000040};" : "=l"(d) : "r"(lo)); return d; }
__device__ __forceinline__ uint64_t d64(uint32_t lo) { uint64_t d; asm("mov.b64 %0, {%1, 0x80000020};" : "=l"(d) : "r"(lo)); return d; }
template<int O,int TB,int ACC,int NN> __device__ __forceinline__ void mma_ss64(float (&d)[NN], uint64_t da, uint64_t db, int sd = 0){
  if constexpr (ACC == 1) asm volatile("wgmma.mma_async.sync.aligned.m64n64k16.f32.bf16.bf16 {%0,%1,%2,%3,%4,%5,%6,%7,%8,%9,%10,%11,%12,%13,%14,%15,%16,%17,%18,%19,%20,%21,%22,%23,%24,%25,%26,%27,%28,%29,%30,%31}, %32, %33, 1, 1, 1, %35, %34;"
   : "+f"(d[O+0]), "+f"(d[O+1]), "+f"(d[O+2]), "+f"(d[O+3]), "+f"(d[O+4]), "+f"(d[O+5]), "+f"(d[O+6]), "+f"(d[O+7]), "+f"(d[O+8]), "+f"(d[O+9]), "+f"(d[O+10]), "+f"(d[O+11]), "+f"(d[O+12]), "+f"(d[O+13]), "+f"(d[O+14]), "+f"(d[O+15]), "+f"(d[O+16]), "+f"(d[O+17]), "+f"(d[O+18]), "+f"(d[O+19]), "+f"(d[O+20]), "+f"(d[O+21]), "+f"(d[O+22]), "+f"(d[O+23]), "+f"(d[O+24]), "+f"(d[O+25]), "+f"(d[O+26]), "+f"(d[O+27]), "+f"(d[O+28]), "+f"(d[O+29]), "+f"(d[O+30]), "+f"(d[O+31])
   : "l"(da), "l"(db), "n"(TB & 1), "n"(TB >> 1));
  else if constexpr (ACC == 0) asm volatile("wgmma.mma_async.sync.aligned.m64n64k16.f32.bf16.bf16 {%0,%1,%2,%3,%4,%5,%6,%7,%8,%9,%10,%11,%12,%13,%14,%15,%16,%17,%18,%19,%20,%21,%22,%23,%24,%25,%26,%27,%28,%29,%30,%31}, %32, %33, 0, 1, 1, %35, %34;"
   : "=f"(d[O+0]), "=f"(d[O+1]), "=f"(d[O+2]), "=f"(d[O+3]), "=f"(d[O+4]), "=f"(d[O+5]), "=f"(d[O+6]), "=f"(d[O+7]), "=f"(d[O+8]), "=f"(d[O+9]), "=f"(d[O+10]), "=f"(d[O+11]), "=f"(d[O+12]), "=f"(d[O+13]), "=f"(d[O+14]), "=f"(d[O+15]), "=f"(d[O+16]), "=f"(d[O+17]), "=f"(d[O+18]), "=f"(d[O+19]), "=f"(d[O+20]), "=f"(d[O+21]), "=f"(d[O+22]), "=f"(d[O+23]), "=f"(d[O+24]), "=f"(d[O+25]), "=f"(d[O+26]), "=f"(d[O+27]), "=f"(d[O+28]), "=f"(d[O+29]), "=f"(d[O+30]), "=f"(d[O+31])
   : "l"(da), "l"(db), "n"(TB & 1), "n"(TB >> 1));
  else asm volatile("{\n.reg .pred p;\nsetp.ne.b32 p, %36, 0;\nwgmma.mma_async.sync.aligned.m64n64k16.f32.bf16.bf16 {%0,%1,%2,%3,%4,%5,%6,%7,%8,%9,%10,%11,%12,%13,%14,%15,%16,%17,%18,%19,%20,%21,%22,%23,%24,%25,%26,%27,%28,%29,%30,%31}, %32, %33, p, 1, 1, %35, %34;\n}"
   : "+f"(d[O+0]), "+f"(d[O+1]), "+f"(d[O+2]), "+f"(d[O+3]), "+f"(d[O+4]), "+f"(d[O+5]), "+f"(d[O+6]), "+f"(d[O+7]), "+f"(d[O+8]), "+f"(d[O+9]), "+f"(d[O+10]), "+f"(d[O+11]), "+f"(d[O+12]), "+f"(d[O+13]), "+f"(d[O+14]), "+f"(d[O+15]), "+f"(d[O+16]), "+f"(d[O+17]), "+f"(d[O+18]), "+f"(d[O+19]), "+f"(d[O+20]), "+f"(d[O+21]), "+f"(d[O+22]), "+f"(d[O+23]), "+f"(d[O+24]), "+f"(d[O+25]), "+f"(d[O+26]), "+f"(d[O+27]), "+f"(d[O+28]), "+f"(d[O+29]), "+f"(d[O+30]), "+f"(d[O+31])
   : "l"(da), "l"(db), "n"(TB & 1), "n"(TB >> 1), "r"(sd));
}
template<int O,int TB,int ACC,int NN> __device__ __forceinline__ void mma_rs64(float (&d)[NN], uint32_t a0, uint32_t a1, uint32_t a2, uint32_t a3, uint64_t db, int sd = 0){
  if constexpr (ACC == 1) asm volatile("wgmma.mma_async.sync.aligned.m64n64k16.f32.bf16.bf16 {%0,%1,%2,%3,%4,%5,%6,%7,%8,%9,%10,%11,%12,%13,%14,%15,%16,%17,%18,%19,%20,%21,%22,%23,%24,%25,%26,%27,%28,%29,%30,%31}, {%32,%33,%34,%35}, %36, 1, 1, 1, %37;"
   : "+f"(d[O+0]), "+f"(d[O+1]), "+f"(d[O+2]), "+f"(d[O+3]), "+f"(d[O+4]), "+f"(d[O+5]), "+f"(d[O+6]), "+f"(d[O+7]), "+f"(d[O+8]), "+f"(d[O+9]), "+f"(d[O+10]), "+f"(d[O+11]), "+f"(d[O+12]), "+f"(d[O+13]), "+f"(d[O+14]), "+f"(d[O+15]), "+f"(d[O+16]), "+f"(d[O+17]), "+f"(d[O+18]), "+f"(d[O+19]), "+f"(d[O+20]), "+f"(d[O+21]), "+f"(d[O+22]), "+f"(d[O+23]), "+f"(d[O+24]), "+f"(d[O+25]), "+f"(d[O+26]), "+f"(d[O+27]), "+f"(d[O+28]), "+f"(d[O+29]), "+f"(d[O+30]), "+f"(d[O+31])
   : "r"(a0), "r"(a1), "r"(a2), "r"(a3), "l"(db), "n"(TB));
  else if constexpr (ACC == 0) asm volatile("wgmma.mma_async.sync.aligned.m64n64k16.f32.bf16.bf16 {%0,%1,%2,%3,%4,%5,%6,%7,%8,%9,%10,%11,%12,%13,%14,%15,%16,%17,%18,%19,%20,%21,%22,%23,%24,%25,%26,%27,%28,%29,%30,%31}, {%32,%33,%34,%35}, %36, 0, 1, 1, %37;"
   : "=f"(d[O+0]), "=f"(d[O+1]), "=f"(d[O+2]), "=f"(d[O+3]), "=f"(d[O+4]), "=f"(d[O+5]), "=f"(d[O+6]), "=f"(d[O+7]), "=f"(d[O+8]), "=f"(d[O+9]), "=f"(d[O+10]), "=f"(d[O+11]), "=f"(d[O+12]), "=f"(d[O+13]), "=f"(d[O+14]), "=f"(d[O+15]), "=f"(d[O+16]), "=f"(d[O+17]), "=f"(d[O+18]), "=f"(d[O+19]), "=f"(d[O+20]), "=f"(d[O+21]), "=f"(d[O+22]), "=f"(d[O+23]), "=f"(d[O+24]), "=f"(d[O+25]), "=f"(d[O+26]), "=f"(d[O+27]), "=f"(d[O+28]), "=f"(d[O+29]), "=f"(d[O+30]), "=f"(d[O+31])
   : "r"(a0), "r"(a1), "r"(a2), "r"(a3), "l"(db), "n"(TB));
  else asm volatile("{\n.reg .pred p;\nsetp.ne.b32 p, %38, 0;\nwgmma.mma_async.sync.aligned.m64n64k16.f32.bf16.bf16 {%0,%1,%2,%3,%4,%5,%6,%7,%8,%9,%10,%11,%12,%13,%14,%15,%16,%17,%18,%19,%20,%21,%22,%23,%24,%25,%26,%27,%28,%29,%30,%31}, {%32,%33,%34,%35}, %36, p, 1, 1, %37;\n}"
   : "+f"(d[O+0]), "+f"(d[O+1]), "+f"(d[O+2]), "+f"(d[O+3]), "+f"(d[O+4]), "+f"(d[O+5]), "+f"(d[O+6]), "+f"(d[O+7]), "+f"(d[O+8]), "+f"(d[O+9]), "+f"(d[O+10]), "+f"(d[O+11]), "+f"(d[O+12]), "+f"(d[O+13]), "+f"(d[O+14]), "+f"(d[O+15]), "+f"(d[O+16]), "+f"(d[O+17]), "+f"(d[O+18]), "+f"(d[O+19]), "+f"(d[O+20]), "+f"(d[O+21]), "+f"(d[O+22]), "+f"(d[O+23]), "+f"(d[O+24]), "+f"(d[O+25]), "+f"(d[O+26]), "+f"(d[O+27]), "+f"(d[O+28]), "+f"(d[O+29]), "+f"(d[O+30]), "+f"(d[O+31])
   : "r"(a0), "r"(a1), "r"(a2), "r"(a3), "l"(db), "n"(TB), "r"(sd));
}
template<int O,int TB,int ACC,int NN> __device__ __forceinline__ void mma_ss128(float (&d)[NN], uint64_t da, uint64_t db, int sd = 0){
  if constexpr (ACC == 1) asm volatile("wgmma.mma_async.sync.aligned.m64n128k16.f32.bf16.bf16 {%0,%1,%2,%3,%4,%5,%6,%7,%8,%9,%10,%11,%12,%13,%14,%15,%16,%17,%18,%19,%20,%21,%22,%23,%24,%25,%26,%27,%28,%29,%30,%31,%32,%33,%34,%35,%36,%37,%38,%39,%40,%41,%42,%43,%44,%45,%46,%47,%48,%49,%50,%51,%52,%53,%54,%55,%56,%57,%58,%59,%60,%61,%62,%63}, %64, %65, 1, 1, 1, %67, %66;"
   : "+f"(d[O+0]), "+f"(d[O+1]), "+f"(d[O+2]), "+f"(d[O+3]), "+f"(d[O+4]), "+f"(d[O+5]), "+f"(d[O+6]), "+f"(d[O+7]), "+f"(d[O+8]), "+f"(d[O+9]), "+f"(d[O+10]), "+f"(d[O+11]), "+f"(d[O+12]), "+f"(d[O+13]), "+f"(d[O+14]), "+f"(d[O+15]), "+f"(d[O+16]), "+f"(d[O+17]), "+f"(d[O+18]), "+f"(d[O+19]), "+f"(d[O+20]), "+f"(d[O+21]), "+f"(d[O+22]), "+f"(d[O+23]), "+f"(d[O+24]), "+f"(d[O+25]), "+f"(d[O+26]), "+f"(d[O+27]), "+f"(d[O+28]), "+f"(d[O+29]), "+f"(d[O+30]), "+f"(d[O+31]), "+f"(d[O+32]), "+f"(d[O+33]), "+f"(d[O+34]), "+f"(d[O+35]), "+f"(d[O+36]), "+f"(d[O+37]), "+f"(d[O+38]), "+f"(d[O+39]), "+f"(d[O+40]), "+f"(d[O+41]), "+f"(d[O+42]), "+f"(d[O+43]), "+f"(d[O+44]), "+f"(d[O+45]), "+f"(d[O+46]), "+f"(d[O+47]), "+f"(d[O+48]), "+f"(d[O+49]), "+f"(d[O+50]), "+f"(d[O+51]), "+f"(d[O+52]), "+f"(d[O+53]), "+f"(d[O+54]), "+f"(d[O+55]), "+f"(d[O+56]), "+f"(d[O+57]), "+f"(d[O+58]), "+f"(d[O+59]), "+f"(d[O+60]), "+f"(d[O+61]), "+f"(d[O+62]), "+f"(d[O+63])
   : "l"(da), "l"(db), "n"(TB & 1), "n"(TB >> 1));
  else if constexpr (ACC == 0) asm volatile("wgmma.mma_async.sync.aligned.m64n128k16.f32.bf16.bf16 {%0,%1,%2,%3,%4,%5,%6,%7,%8,%9,%10,%11,%12,%13,%14,%15,%16,%17,%18,%19,%20,%21,%22,%23,%24,%25,%26,%27,%28,%29,%30,%31,%32,%33,%34,%35,%36,%37,%38,%39,%40,%41,%42,%43,%44,%45,%46,%47,%48,%49,%50,%51,%52,%53,%54,%55,%56,%57,%58,%59,%60,%61,%62,%63}, %64, %65, 0, 1, 1, %67, %66;"
   : "=f"(d[O+0]), "=f"(d[O+1]), "=f"(d[O+2]), "=f"(d[O+3]), "=f"(d[O+4]), "=f"(d[O+5]), "=f"(d[O+6]), "=f"(d[O+7]), "=f"(d[O+8]), "=f"(d[O+9]), "=f"(d[O+10]), "=f"(d[O+11]), "=f"(d[O+12]), "=f"(d[O+13]), "=f"(d[O+14]), "=f"(d[O+15]), "=f"(d[O+16]), "=f"(d[O+17]), "=f"(d[O+18]), "=f"(d[O+19]), "=f"(d[O+20]), "=f"(d[O+21]), "=f"(d[O+22]), "=f"(d[O+23]), "=f"(d[O+24]), "=f"(d[O+25]), "=f"(d[O+26]), "=f"(d[O+27]), "=f"(d[O+28]), "=f"(d[O+29]), "=f"(d[O+30]), "=f"(d[O+31]), "=f"(d[O+32]), "=f"(d[O+33]), "=f"(d[O+34]), "=f"(d[O+35]), "=f"(d[O+36]), "=f"(d[O+37]), "=f"(d[O+38]), "=f"(d[O+39]), "=f"(d[O+40]), "=f"(d[O+41]), "=f"(d[O+42]), "=f"(d[O+43]), "=f"(d[O+44]), "=f"(d[O+45]), "=f"(d[O+46]), "=f"(d[O+47]), "=f"(d[O+48]), "=f"(d[O+49]), "=f"(d[O+50]), "=f"(d[O+51]), "=f"(d[O+52]), "=f"(d[O+53]), "=f"(d[O+54]), "=f"(d[O+55]), "=f"(d[O+56]), "=f"(d[O+57]), "=f"(d[O+58]), "=f"(d[O+59]), "=f"(d[O+60]), "=f"(d[O+61]), "=f"(d[O+62]), "=f"(d[O+63])
   : "l"(da), "l"(db), "n"(TB & 1), "n"(TB >> 1));
  else asm volatile("{\n.reg .pred p;\nsetp.ne.b32 p, %68, 0;\nwgmma.mma_async.sync.aligned.m64n128k16.f32.bf16.bf16 {%0,%1,%2,%3,%4,%5,%6,%7,%8,%9,%10,%11,%12,%13,%14,%15,%16,%17,%18,%19,%20,%21,%22,%23,%24,%25,%26,%27,%28,%29,%30,%31,%32,%33,%34,%35,%36,%37,%38,%39,%40,%41,%42,%43,%44,%45,%46,%47,%48,%49,%50,%51,%52,%53,%54,%55,%56,%57,%58,%59,%60,%61,%62,%63}, %64, %65, p, 1, 1, %67, %66;\n}"
   : "+f"(d[O+0]), "+f"(d[O+1]), "+f"(d[O+2]), "+f"(d[O+3]), "+f"(d[O+4]), "+f"(d[O+5]), "+f"(d[O+6]), "+f"(d[O+7]), "+f"(d[O+8]), "+f"(d[O+9]), "+f"(d[O+10]), "+f"(d[O+11]), "+f"(d[O+12]), "+f"(d[O+13]), "+f"(d[O+14]), "+f"(d[O+15]), "+f"(d[O+16]), "+f"(d[O+17]), "+f"(d[O+18]), "+f"(d[O+19]), "+f"(d[O+20]), "+f"(d[O+21]), "+f"(d[O+22]), "+f"(d[O+23]), "+f"(d[O+24]), "+f"(d[O+25]), "+f"(d[O+26]), "+f"(d[O+27]), "+f"(d[O+28]), "+f"(d[O+29]), "+f"(d[O+30]), "+f"(d[O+31]), "+f"(d[O+32]), "+f"(d[O+33]), "+f"(d[O+34]), "+f"(d[O+35]), "+f"(d[O+36]), "+f"(d[O+37]), "+f"(d[O+38]), "+f"(d[O+39]), "+f"(d[O+40]), "+f"(d[O+41]), "+f"(d[O+42]), "+f"(d[O+43]), "+f"(d[O+44]), "+f"(d[O+45]), "+f"(d[O+46]), "+f"(d[O+47]), "+f"(d[O+48]), "+f"(d[O+49]), "+f"(d[O+50]), "+f"(d[O+51]), "+f"(d[O+52]), "+f"(d[O+53]), "+f"(d[O+54]), "+f"(d[O+55]), "+f"(d[O+56]), "+f"(d[O+57]), "+f"(d[O+58]), "+f"(d[O+59]), "+f"(d[O+60]), "+f"(d[O+61]), "+f"(d[O+62]), "+f"(d[O+63])
   : "l"(da), "l"(db), "n"(TB & 1), "n"(TB >> 1), "r"(sd));
}
template<int O,int TB,int ACC,int NN> __device__ __forceinline__ void mma_rs128(float (&d)[NN], uint32_t a0, uint32_t a1, uint32_t a2, uint32_t a3, uint64_t db, int sd = 0){
  if constexpr (ACC == 1) asm volatile("wgmma.mma_async.sync.aligned.m64n128k16.f32.bf16.bf16 {%0,%1,%2,%3,%4,%5,%6,%7,%8,%9,%10,%11,%12,%13,%14,%15,%16,%17,%18,%19,%20,%21,%22,%23,%24,%25,%26,%27,%28,%29,%30,%31,%32,%33,%34,%35,%36,%37,%38,%39,%40,%41,%42,%43,%44,%45,%46,%47,%48,%49,%50,%51,%52,%53,%54,%55,%56,%57,%58,%59,%60,%61,%62,%63}, {%64,%65,%66,%67}, %68, 1, 1, 1, %69;"
   : "+f"(d[O+0]), "+f"(d[O+1]), "+f"(d[O+2]), "+f"(d[O+3]), "+f"(d[O+4]), "+f"(d[O+5]), "+f"(d[O+6]), "+f"(d[O+7]), "+f"(d[O+8]), "+f"(d[O+9]), "+f"(d[O+10]), "+f"(d[O+11]), "+f"(d[O+12]), "+f"(d[O+13]), "+f"(d[O+14]), "+f"(d[O+15]), "+f"(d[O+16]), "+f"(d[O+17]), "+f"(d[O+18]), "+f"(d[O+19]), "+f"(d[O+20]), "+f"(d[O+21]), "+f"(d[O+22]), "+f"(d[O+23]), "+f"(d[O+24]), "+f"(d[O+25]), "+f"(d[O+26]), "+f"(d[O+27]), "+f"(d[O+28]), "+f"(d[O+29]), "+f"(d[O+30]), "+f"(d[O+31]), "+f"(d[O+32]), "+f"(d[O+33]), "+f"(d[O+34]), "+f"(d[O+35]), "+f"(d[O+36]), "+f"(d[O+37]), "+f"(d[O+38]), "+f"(d[O+39]), "+f"(d[O+40]), "+f"(d[O+41]), "+f"(d[O+42]), "+f"(d[O+43]), "+f"(d[O+44]), "+f"(d[O+45]), "+f"(d[O+46]), "+f"(d[O+47]), "+f"(d[O+48]), "+f"(d[O+49]), "+f"(d[O+50]), "+f"(d[O+51]), "+f"(d[O+52]), "+f"(d[O+53]), "+f"(d[O+54]), "+f"(d[O+55]), "+f"(d[O+56]), "+f"(d[O+57]), "+f"(d[O+58]), "+f"(d[O+59]), "+f"(d[O+60]), "+f"(d[O+61]), "+f"(d[O+62]), "+f"(d[O+63])
   : "r"(a0), "r"(a1), "r"(a2), "r"(a3), "l"(db), "n"(TB));
  else if constexpr (ACC == 0) asm volatile("wgmma.mma_async.sync.aligned.m64n128k16.f32.bf16.bf16 {%0,%1,%2,%3,%4,%5,%6,%7,%8,%9,%10,%11,%12,%13,%14,%15,%16,%17,%18,%19,%20,%21,%22,%23,%24,%25,%26,%27,%28,%29,%30,%31,%32,%33,%34,%35,%36,%37,%38,%39,%40,%41,%42,%43,%44,%45,%46,%47,%48,%49,%50,%51,%52,%53,%54,%55,%56,%57,%58,%59,%60,%61,%62,%63}, {%64,%65,%66,%67}, %68, 0, 1, 1, %69;"
   : "=f"(d[O+0]), "=f"(d[O+1]), "=f"(d[O+2]), "=f"(d[O+3]), "=f"(d[O+4]), "=f"(d[O+5]), "=f"(d[O+6]), "=f"(d[O+7]), "=f"(d[O+8]), "=f"(d[O+9]), "=f"(d[O+10]), "=f"(d[O+11]), "=f"(d[O+12]), "=f"(d[O+13]), "=f"(d[O+14]), "=f"(d[O+15]), "=f"(d[O+16]), "=f"(d[O+17]), "=f"(d[O+18]), "=f"(d[O+19]), "=f"(d[O+20]), "=f"(d[O+21]), "=f"(d[O+22]), "=f"(d[O+23]), "=f"(d[O+24]), "=f"(d[O+25]), "=f"(d[O+26]), "=f"(d[O+27]), "=f"(d[O+28]), "=f"(d[O+29]), "=f"(d[O+30]), "=f"(d[O+31]), "=f"(d[O+32]), "=f"(d[O+33]), "=f"(d[O+34]), "=f"(d[O+35]), "=f"(d[O+36]), "=f"(d[O+37]), "=f"(d[O+38]), "=f"(d[O+39]), "=f"(d[O+40]), "=f"(d[O+41]), "=f"(d[O+42]), "=f"(d[O+43]), "=f"(d[O+44]), "=f"(d[O+45]), "=f"(d[O+46]), "=f"(d[O+47]), "=f"(d[O+48]), "=f"(d[O+49]), "=f"(d[O+50]), "=f"(d[O+51]), "=f"(d[O+52]), "=f"(d[O+53]), "=f"(d[O+54]), "=f"(d[O+55]), "=f"(d[O+56]), "=f"(d[O+57]), "=f"(d[O+58]), "=f"(d[O+59]), "=f"(d[O+60]), "=f"(d[O+61]), "=f"(d[O+62]), "=f"(d[O+63])
   : "r"(a0), "r"(a1), "r"(a2), "r"(a3), "l"(db), "n"(TB));
  else asm volatile("{\n.reg .pred p;\nsetp.ne.b32 p, %70, 0;\nwgmma.mma_async.sync.aligned.m64n128k16.f32.bf16.bf16 {%0,%1,%2,%3,%4,%5,%6,%7,%8,%9,%10,%11,%12,%13,%14,%15,%16,%17,%18,%19,%20,%21,%22,%23,%24,%25,%26,%27,%28,%29,%30,%31,%32,%33,%34,%35,%36,%37,%38,%39,%40,%41,%42,%43,%44,%45,%46,%47,%48,%49,%50,%51,%52,%53,%54,%55,%56,%57,%58,%59,%60,%61,%62,%63}, {%64,%65,%66,%67}, %68, p, 1, 1, %69;\n}"
   : "+f"(d[O+0]), "+f"(d[O+1]), "+f"(d[O+2]), "+f"(d[O+3]), "+f"(d[O+4]), "+f"(d[O+5]), "+f"(d[O+6]), "+f"(d[O+7]), "+f"(d[O+8]), "+f"(d[O+9]), "+f"(d[O+10]), "+f"(d[O+11]), "+f"(d[O+12]), "+f"(d[O+13]), "+f"(d[O+14]), "+f"(d[O+15]), "+f"(d[O+16]), "+f"(d[O+17]), "+f"(d[O+18]), "+f"(d[O+19]), "+f"(d[O+20]), "+f"(d[O+21]), "+f"(d[O+22]), "+f"(d[O+23]), "+f"(d[O+24]), "+f"(d[O+25]), "+f"(d[O+26]), "+f"(d[O+27]), "+f"(d[O+28]), "+f"(d[O+29]), "+f"(d[O+30]), "+f"(d[O+31]), "+f"(d[O+32]), "+f"(d[O+33]), "+f"(d[O+34]), "+f"(d[O+35]), "+f"(d[O+36]), "+f"(d[O+37]), "+f"(d[O+38]), "+f"(d[O+39]), "+f"(d[O+40]), "+f"(d[O+41]), "+f"(d[O+42]), "+f"(d[O+43]), "+f"(d[O+44]), "+f"(d[O+45]), "+f"(d[O+46]), "+f"(d[O+47]), "+f"(d[O+48]), "+f"(d[O+49]), "+f"(d[O+50]), "+f"(d[O+51]), "+f"(d[O+52]), "+f"(d[O+53]), "+f"(d[O+54]), "+f"(d[O+55]), "+f"(d[O+56]), "+f"(d[O+57]), "+f"(d[O+58]), "+f"(d[O+59]), "+f"(d[O+60]), "+f"(d[O+61]), "+f"(d[O+62]), "+f"(d[O+63])
   : "r"(a0), "r"(a1), "r"(a2), "r"(a3), "l"(db), "n"(TB), "r"(sd));
}

#define NEARLY 0
#define XAHEAD 3
#define HM 2
#define WBATCH 1
#define SPACE 0
#define WPF 0
#define WAFTER 7
#define WPACE 0
#define GATE_AT 4
#define TPACE 40
#define PFMODE 0
#define MAPMODE 0
template <int V> struct IC { static constexpr int value = V; };
struct Maps { CUtensorMap x, ft, g64, u64, e, wr, wi, xs, ts, t, g32, u32, d224; };

constexpr int NCTA = 130;
constexpr int U = 16384;
constexpr int TB = 36864;
constexpr int OFF_RING = 8 * U, OFF_Z = 9 * U, OFF_XB = 12 * U, OFF_T = 13 * U, OFF_D = OFF_T;
constexpr int OFF_BAR = 14 * U, OFF_SP = OFF_BAR + 512, OFF_G = OFF_SP + 1024 + 128;
constexpr int SMEM_BYTES = OFF_G + 512;
constexpr int B_FX = 0, B_FA = 8, B_FT = 12, B_Z = 16, B_W = 20, B_HX = 21, B_TL = 22, B_HP = 23, B_WR = 26, B_E0 = 30;
constexpr int B_EA = 31, B_ET = 35, B_PZ = 39, B_RDY = 41, B_FE = 42;
constexpr int B_T = 46, B_XS = 47, B_G = 49, NBAR = 50;
__host__ __device__ constexpr int rslot(int n) { return n & 3; }
__host__ __device__ constexpr int rpar(int n) { return (n >> 2) & 1; }

__global__ void __cluster_dims__(2, 1, 1) __launch_bounds__(512, 1)
fused_kernel(const __grid_constant__ Maps maps, const __nv_bfloat16* __restrict__ w_r,
             const __nv_bfloat16* __restrict__ w_i, const __nv_bfloat16* __restrict__ gate_w, __nv_bfloat16* __restrict__ out) {
  extern __shared__ __align__(1024) uint8_t smem[];
  const uint32_t sb = smem_u32(smem);
  const uint32_t bars = sb + OFF_BAR;
  const int tid = threadIdx.x, lane = tid & 31;
  const int warp = __shfl_sync(0xffffffffu, tid >> 5, 0);
  const bool helper = blockIdx.x >= 128;
  const int cl = (blockIdx.x >> 1) & 63, rank = blockIdx.x & 1;
  const int q4 = cl & 3, rb = cl >> 2;
  const int j = 2 * q4 + rank;
  const int f_full = 448 * q4 + (rank ? 256 : 0);
  const int f_half = 448 * q4 + (rank ? 224 : 192);
  const int kg = 2 * j + (rb >> 3), tn = rb & 7;

  if (tid == 64) { PROF_EV(0); PROF_CK(40); }
  if (warp < 8) {
    asm volatile("barrier.cluster.arrive.relaxed.aligned;" ::: "memory");
    asm volatile("setmaxnreg.inc.sync.aligned.u32 192;");
    if (!helper) {
      const int wg = warp >> 2, w = warp & 3, g = lane >> 2;
      const bool elect = (tid & 127) == 0;
      float cX[32], cA[64], cB[64], cC[64], ci[64], ct[64];
      const int zero = blockIdx.x >> 16;
      uint32_t h[56], yf[16];
      const uint32_t d0 = (sb & 0x3FFFF) >> 4;
      const uint32_t dK = d0 | (1u << 16), dN = d0 | (512u << 16);
      const uint32_t dX = dK + wg * 512;
      constexpr uint32_t RING = OFF_RING >> 4;
      auto waitA = [&](int n) { mbar_wait(bars + 8 * (B_FA + rslot(n)), rpar(n)); };
      auto freeA = [&](int n) { mbar_arrive_if(elect, bars + 8 * (B_EA + rslot(n))); };
      auto nop = [] {};

      asm volatile("bar.sync 0, 384;" ::: "memory");
#pragma unroll 1
      for (int i = 0; i < 4; i++) {
        const uint64_t dx = d128(dX + i * 2048), df = d128(dK + (OFF_XB >> 4) + (i & 1) * 1024);
        mbar_wait(bars + 8 * (B_FX + 2 * i), 0);
        wg_fence();
        mma_ss64<0, 0, 2>(cX, df, dx, i);
        mma_ss64<0, 0, 1>(cX, df + 2, dx + 2);
        wg_commit(); wg_wait<1>();
        mbar_arrive_if(elect && i, bars + 8 * (B_EA + rslot(i - 1)));
        mma_ss64<0, 0, 1>(cX, df + 4, dx + 4);
        mma_ss64<0, 0, 1>(cX, df + 6, dx + 6);
        if (i == 0 && tid == 0) PROF_EV(1);
        mbar_wait(bars + 8 * (B_FX + 2 * i + 1), 0);
        wg_fence();
#pragma unroll
        for (int k = 0; k < 4; k++) mma_ss64<0, 0, 1>(cX, df + (512 + k * 2), dx + (1024 + k * 2));
        wg_commit();
        waitA(i);
        wg_fence();
        const uint64_t da = d128(dX + i * 1024), db = d128(dN + RING + i * 1024);
        mma_ss128<0, 1, 2>(cA, da, db, i);
        wg_commit(); wg_wait<1>();
        mbar_arrive_if(elect, bars + 8 * (B_FE + i));
#pragma unroll
        for (int k = 1; k < 4; k++) mma_ss128<0, 1, 1>(cA, da + k * 2, db + k * 128);
        wg_commit();
      }
      fence_regs<0, 32>(cX);
#pragma unroll
      for (int e = 0; e < 16; e++) yf[e] = pack_pin(cX[2 * e], cX[2 * e + 1]);
      if (tid == 0) PROF_EV(2);
      {
        waitA(4); mbar_wait(bars + 8 * B_E0, 0);
        const uint64_t de = d128(dN + (wg ? RING : OFF_XB >> 4));
        wg_fence();
        mma_rs128<0, 1, 0>(cB, yf[0], yf[1], yf[2], yf[3], de);
        wg_commit();
        wg_wait<1>();
        freeA(3);
#pragma unroll
        for (int k = 1; k < 4; k++) mma_rs128<0, 1, 1>(cB, yf[4 * k], yf[4 * k + 1], yf[4 * k + 2], yf[4 * k + 3], de + k * 128);
        wg_commit();
      }
      bool rel = false;
      auto acquire = [&](int n) {
        rel = elect;
        if (!mbar_try(bars + 8 * (B_FA + rslot(n)), rpar(n))) { wg_wait<0>(); freeA(n - 1); rel = false; waitA(n); }
      };
      auto freeP = [&](int n) { mbar_arrive_if(rel, bars + 8 * (B_EA + rslot(n - 1))); };
      auto ffn_step = [&](auto first, auto split, float (&acc)[64], int n, int kb, auto done, auto work) {
        constexpr int SPLIT = decltype(split)::value;
        acquire(n);
        wg_fence();
        const uint64_t dx = d128(dX + kb * 1024), db = d128(dN + RING + rslot(n) * 1024);
        mma_ss128<0, 1, decltype(first)::value>(acc, dx, db, zero);
#pragma unroll
        for (int k = 1; k < SPLIT; k++) mma_ss128<0, 1, 1>(acc, dx + k * 2, db + k * 128);
        wg_commit();
        work();
        wg_wait<1>();
        freeP(n);
        done();
        if (SPLIT < 4) {
          wg_fence();
#pragma unroll
          for (int k = SPLIT; k < 4; k++) mma_ss128<0, 1, 1>(acc, dx + k * 2, db + k * 128);
          wg_commit();
        }
      };
      {
        const int s0 = 2 * rb + wg, kr = 2 * ((s0 & 1) | ((s0 & 4) >> 1));
        const int m = lane >> 3, r = lane & 7;
        const uint32_t a0 = sb + OFF_XB + wg * 8192 + (((w >> 1) * 8 + (m >> 1)) * 2 + (w & 1)) * 256 + (m & 1) * 128 + ((r ^ (kr + (m & 1))) << 4);
        ffn_step(IC<1>(), IC<4>(), cA, 5, 4, [&] { fence_regs<0, 64>(cB); }, nop);
        asm volatile("bar.sync 5, 256;" ::: "memory");
#pragma unroll
        for (int i = 0; i < 4; i++)
          stsm4t(a0 + i * 1024, pack_bf16(cB[8 * i] - cB[34 + 8 * i], cB[8 * i + 1] - cB[35 + 8 * i]),
                 pack_bf16(cB[32 + 8 * i] + cB[8 * i + 2], cB[33 + 8 * i] + cB[8 * i + 3]),
                 pack_bf16(cB[8 * i + 4] - cB[38 + 8 * i], cB[8 * i + 5] - cB[39 + 8 * i]),
                 pack_bf16(cB[36 + 8 * i] + cB[8 * i + 6], cB[37 + 8 * i] + cB[8 * i + 7]));
        if (j == 0 && w == 0) {
          const uint32_t a1 = r ? sb + OFF_SP + 1024 : sb + OFF_SP + wg * 512 + (m & 1) * 256 + (m >> 1) * 128;
#pragma unroll
          for (int n = 0; n < 8; n++)
            asm volatile("stmatrix.sync.aligned.m8n8.x4.shared.b16 [%0], {%1,%2,%3,%4};" ::"r"(a1 + ((n ^ (kr + (m >> 1))) << 4)),
                         "r"(pack_bf16(cB[4 * n], cB[4 * n + 1])), "r"(pack_bf16(cB[4 * n + 2], cB[4 * n + 3])),
                         "r"(pack_bf16(cB[32 + 4 * n], cB[33 + 4 * n])), "r"(pack_bf16(cB[34 + 4 * n], cB[35 + 4 * n])) : "memory");
        }
        ffn_step(IC<1>(), IC<2>(), cA, 6, 5, nop, [&] {
          asm volatile("fence.proxy.async.shared::cta;" ::: "memory");
          __syncwarp();
          mbar_arrive_if(lane == 0, bars + 8 * (B_XS + wg));
          if (tid == 0) PROF_EV(3);
        });
      }
#pragma unroll 1
      for (int kb = 6; kb < 8; kb++) ffn_step(IC<1>(), IC<1>(), cA, 1 + kb, kb, nop, nop);
      ffn_step(IC<2>(), IC<1>(), cB, 9, 0, [&] { fence_regs<0, 64>(cA); }, nop);
#pragma unroll 1
      for (int kb = 1; kb < 6; kb++) ffn_step(IC<1>(), IC<1>(), cB, 9 + kb, kb, nop, nop);
      mbar_wait(bars + 8 * B_G, 0);
      const uint32_t gb0 = *(const uint32_t*)(smem + OFF_G + (wg * 64 + w * 16 + g) * 4), gb1 = *(const uint32_t*)(smem + OFF_G + (wg * 64 + w * 16 + g + 8) * 4);
      const uint32_t tag = gb0 & 1;
      const float g0 = __uint_as_float(gb0 & ~1u), g1 = __uint_as_float(gb1 & ~1u);
      const float o0 = 1.0f - g0, o1 = 1.0f - g1;
      auto glu = [&](auto& acc, int half, int ho, int i0, int i1) {
#pragma unroll
        for (int i = i0; i < i1; i++) {
          const float o = (i & 1) ? o1 : o0;
          h[ho + i] = pack_pin(fmaxf(acc[2 * i], 0.f) * acc[half + 2 * i] * o, fmaxf(acc[2 * i + 1], 0.f) * acc[half + 1 + 2 * i] * o);
        }
      };
      ffn_step(IC<1>(), IC<1>(), cB, 15, 6, nop, [&] { glu(cA, 32, 0, 0, 8); });
      ffn_step(IC<1>(), IC<1>(), cB, 16, 7, nop, [&] { glu(cA, 32, 0, 8, 16); });
      ffn_step(IC<0>(), IC<1>(), cC, 17, 0, [&] { fence_regs<0, 64>(cB); }, nop);
      if (tid == 0) PROF_EV(4);
      ffn_step(IC<1>(), IC<1>(), cC, 18, 1, nop, [&] { glu(cB, 32, 16, 0, 8); });
      ffn_step(IC<1>(), IC<1>(), cC, 19, 2, nop, [&] { glu(cB, 32, 16, 8, 16); });
#pragma unroll 1
      for (int kb = 3; kb < 8; kb++) ffn_step(IC<1>(), IC<1>(), cC, 17 + kb, kb, nop, nop);
      if (tid == 0) PROF_EV(5);
      auto m_step = [&](auto first, int i, auto done, auto work) {
        acquire(25 + i);
        wg_fence();
        const uint64_t dx = d128(dX + i * 2048), dm = d64(dN + RING + rslot(25 + i) * 1024);
        mma_ss64<0, 1, decltype(first)::value>(ct, dx, dm);
        mma_ss64<0, 1, 1>(ct, dx + 2, dm + 64);
        wg_commit();
        work();
        wg_wait<1>();
        freeP(25 + i);
        done();
        wg_fence();
#pragma unroll
        for (int k = 2; k < 8; k++) mma_ss64<0, 1, 1>(ct, dx + ((k >> 2) * 1024 + (k & 3) * 2), dm + k * 64);
        wg_commit();
      };
      auto freeT = [&](int t) { mbar_arrive_if(elect, bars + 8 * (B_ET + t)); };
      m_step(IC<0>(), 0, [&] { fence_regs<0, 64>(cC); }, nop);
      m_step(IC<1>(), 1, [&] { freeT(0); }, [&] { glu(cC, 32, 32, 0, 5); });
      m_step(IC<1>(), 2, [&] { freeT(1); }, [&] { glu(cC, 32, 32, 5, 11); });
      m_step(IC<1>(), 3, [&] { freeT(2); }, [&] { glu(cC, 32, 32, 11, 16); });
      waitA(29 + wg);
      if (tid == 0) PROF_EV(6);
      mbar_wait(bars + 8 * (j == 0 ? B_T : B_TL), 0);
      if (tid == 0) PROF_EV(7);
      wg_fence();
      {
        const uint64_t dt = d128(dN + (OFF_T >> 4) + wg * 512), de = d128(dK + RING + (1 + wg) * 1024);
        mma_ss64<0, 1, 0>(ci, de, dt);
        mma_ss64<32, 1, 0>(ci, de + 512, dt);
#pragma unroll
        for (int k = 1; k < 4; k++) {
          mma_ss64<0, 1, 1>(ci, de + k * 2, dt + k * 128);
          mma_ss64<32, 1, 1>(ci, de + (512 + k * 2), dt + k * 128);
        }
        wg_commit();
        wg_wait<1>();
        freeT(3);
        fence_regs<0, 32>(ct);
        glu(ct, 16, 48, 0, 8);
      }

      auto head = [&](auto off, int t, auto first) {
        constexpr int O = decltype(off)::value;
        mbar_wait(bars + 8 * (B_FT + (t & 3)), t >> 2);
        const uint64_t db = d128(dN + (t & 3) * (TB >> 4) + rank * 256);
        wg_fence();
        mma_rs64<O, 1, decltype(first)::value>(ct, h[0], h[1], h[2], h[3], db, zero);
#pragma unroll
        for (int k = 1; k < 6; k++) mma_rs64<O, 1, 1>(ct, h[4 * k], h[4 * k + 1], h[4 * k + 2], h[4 * k + 3], db + k * 128);
        wg_commit();
        wg_wait<1>();
      };
      auto rest = [&](auto off, int t) {
        constexpr int O = decltype(off)::value;
        const uint64_t db = d128(dN + (t & 3) * (TB >> 4)), dw = db + rank * 256, dm = db + (rank ? 0 : 1536);
        wg_fence();
#pragma unroll
        for (int k = 6; k < 12; k++) mma_rs64<O, 1, 1>(ct, h[4 * k], h[4 * k + 1], h[4 * k + 2], h[4 * k + 3], dw + k * 128);
#pragma unroll
        for (int k = 0; k < 2; k++) mma_rs64<O, 1, 1>(ct, h[48 + 4 * k], h[49 + 4 * k], h[50 + 4 * k], h[51 + 4 * k], dm + k * 128);
#pragma unroll
        for (int k = 0; k < 4; k++) mma_rs64<O, 1, 1>(ct, yf[4 * k], yf[4 * k + 1], yf[4 * k + 2], yf[4 * k + 3], db + (14 + k) * 128);
        wg_commit();
      };
      const uint32_t peerZ = mapa(sb + OFF_Z + tid * 16, rank ^ 1), peerB = mapa(bars + 8 * B_Z, rank ^ 1);
      auto send = [&](auto off, int t) {
        constexpr int O = decltype(off)::value;
        fence_regs<O, 32>(ct);
        const bool grid = t >= 3 && t < 6;
        const int z = grid ? t - 3 : t == 6 ? 3 : t;
        if (grid) {
          mbar_wait(bars + 8 * (B_Z + z), 0);
#pragma unroll
          for (int i = 0; i < 4; i++) {
            const uint4 p = *(const uint4*)(smem + OFF_Z + z * U + i * 4096 + tid * 16);
            const uint32_t a[4] = {p.x, p.y, p.z, p.w};
#pragma unroll
            for (int e = 0; e < 4; e++) { ct[O + 8 * i + 2 * e] += bf_lo(a[e]); ct[O + 8 * i + 2 * e + 1] += bf_hi(a[e]); }
          }
        }
        uint32_t pk[16];
#pragma unroll
        for (int i = 0; i < 16; i++) pk[i] = pack_bf16(ct[O + 2 * i], ct[O + 2 * i + 1]);
        if (grid) {
          const int owner = rb * 8 + 2 * ((q4 + z + 1) & 3) + rank;
          uint4* dst = g_part + (size_t)(owner * 3 + z) * 1024 + tid;
#pragma unroll
          for (int i = 0; i < 4; i++) st_x4(dst + i * 256, (pk[4 * i] & ~1u) | tag, pk[4 * i + 1], pk[4 * i + 2], pk[4 * i + 3]);
          __syncwarp();
          hint_add_if(lane == 0, &g_cntP[32 * owner + z]);
        } else {
#pragma unroll
          for (int i = 0; i < 4; i++)
            asm volatile("st.async.weak.shared::cluster.mbarrier::complete_tx::bytes.v4.b32 [%0], {%1,%2,%3,%4}, [%5];" ::"r"(peerZ + z * U + i * 4096),
                         "r"(pk[4 * i]), "r"(pk[4 * i + 1]), "r"(pk[4 * i + 2]), "r"(pk[4 * i + 3]), "r"(peerB + 8 * z) : "memory");
        }
      };
      asm volatile("barrier.cluster.wait.aligned;" ::: "memory");
      head(IC<0>(), 0, IC<2>());
      if (elect) asm volatile("mbarrier.arrive.shared::cluster.b64 _, [%0];" ::"r"(mapa(bars + 8 * B_RDY, rank ^ 1)) : "memory");
      fence_regs<0, 64>(ci);
#pragma unroll
      for (int i = 0; i < 16; i++) {
        const float gg = ((i & 1) ? g1 : g0) * (2.0f / (2048.0f * 512.0f));
        if (i & 2) yf[i] = pack_pin((ci[2 * i] - ci[28 + 2 * i]) * gg, (ci[2 * i + 1] - ci[29 + 2 * i]) * gg);
        else yf[i] = pack_pin((ci[2 * i] + ci[36 + 2 * i]) * gg, (ci[2 * i + 1] + ci[37 + 2 * i]) * gg);
      }
      if (tid == 0) PROF_EV(8);
#pragma unroll 1
      for (int t = 0;; t += 2) {
        rest(IC<0>(), t);
        head(IC<32>(), t + 1, IC<2>());
        mbar_arrive_if(elect && t < 6, bars + 8 * (B_ET + t));
        if (t == 0) mbar_wait(bars + 8 * B_RDY, 0);
        send(IC<0>(), t);
        rest(IC<32>(), t + 1);
        if (t == 6) break;
        head(IC<0>(), t + 2, IC<2>());
        mbar_arrive_if(elect, bars + 8 * (B_ET + t + 1));
        send(IC<32>(), t + 1);
      }
      if (tid == 0) PROF_EV(9);
      {
        float sum[32];
        mbar_wait(bars + 8 * (B_Z + 3), 0);
#pragma unroll
        for (int i = 0; i < 4; i++) {
          const uint4 p = *(const uint4*)(smem + OFF_Z + 3 * U + i * 4096 + tid * 16);
          const uint32_t a[4] = {p.x, p.y, p.z, p.w};
#pragma unroll
          for (int e = 0; e < 4; e++) { sum[8 * i + 2 * e] = bf_lo(a[e]); sum[8 * i + 2 * e + 1] = bf_hi(a[e]); }
        }
#pragma unroll 1
        for (int z = 0; z < 3; z++) {
          mbar_wait(bars + 8 * (B_HP + z), 0);
          if (z == 2 && tid == 0) PROF_EV(24);
          uint4 pv[4];
#pragma unroll
          for (int i = 0; i < 4; i++) pv[i] = *(const uint4*)(smem + z * U + i * 4096 + tid * 16);
          const uint32_t t0 = (uint32_t)clock();
          while (__any_sync(0xffffffffu, ((pv[0].x ^ tag) | (pv[1].x ^ tag) | (pv[2].x ^ tag) | (pv[3].x ^ tag)) & 1)) {
#pragma unroll
            for (int i = 0; i < 4; i++) pv[i] = ld_x4(g_part + (size_t)((rb * 8 + j) * 3 + z) * 1024 + tid + i * 256);
            spin_guard(t0);
          }
#pragma unroll
          for (int i = 0; i < 4; i++) {
            const uint32_t a[4] = {pv[i].x & ~1u, pv[i].y, pv[i].z, pv[i].w};
#pragma unroll
            for (int e = 0; e < 4; e++) { sum[8 * i + 2 * e] += bf_lo(a[e]); sum[8 * i + 2 * e + 1] += bf_hi(a[e]); }
          }
        }
        if (tid == 0) PROF_EV(14);
        wg_wait<0>();
        fence_regs<32, 32>(ct);
#pragma unroll
        for (int i = 0; i < 32; i++) sum[i] += ct[32 + i];
        const uint32_t stg = sb + OFF_T + warp * 2048;
        const int mr = (lane & 7) + ((lane >> 3) & 1) * 8, mc = lane >> 4;
#pragma unroll
        for (int i = 0; i < 4; i++) {
          const uint32_t a = stg + mr * 128 + (((2 * i + mc) ^ (mr & 7)) << 4);
          asm volatile("stmatrix.sync.aligned.m8n8.x4.shared.b16 [%0], {%1,%2,%3,%4};" ::"r"(a), "r"(pack_bf16(sum[8 * i], sum[8 * i + 1])),
                       "r"(pack_bf16(sum[8 * i + 2], sum[8 * i + 3])), "r"(pack_bf16(sum[8 * i + 4], sum[8 * i + 5])),
                       "r"(pack_bf16(sum[8 * i + 6], sum[8 * i + 7])) : "memory");
        }
        __syncwarp();
#pragma unroll
        for (int i = 0; i < 4; i++) {
          const int r = 4 * i + (lane >> 3), c = lane & 7;
          const uint4 v = *(const uint4*)(smem + OFF_T + warp * 2048 + r * 128 + ((c ^ (r & 7)) << 4));
          *(uint4*)(out + (size_t)(2 * rb + wg + 32 * (16 * w + r)) * 512 + 64 * j + 8 * c) = v;
        }
      }
      if (tid == 0) { PROF_EV(15); PROF_CK(41); }
    }
  } else if (warp < 12) {
    asm volatile("setmaxnreg.dec.sync.aligned.u32 104;");
    asm volatile("barrier.cluster.arrive.relaxed.aligned;" ::: "memory");
    const int t = tid - 256, w = warp - 8;
    const uint32_t ep = ld_x1(&g_epoch[blockIdx.x * 8]);
    const uint32_t tag = (ep + 1) & 1;
    auto gate_rows = [&] {
      const int r = 16 * j + 4 * w + (lane >> 3);
      const uint4* pg = (const uint4*)gate_w + (lane & 7);
      {
        float a = 0.f;
        uint4 vn = __ldg(pg);
        asm volatile("bar.sync 4, 256;" ::: "memory");
#pragma unroll 1
        for (int kb = 0; kb < 8; kb++) {
          const uint4 v = vn;
          vn = __ldg(pg + ((kb + 1) & 7) * 8);
          mbar_wait(bars + 8 * (B_FX + kb), 0);
          const uint4 u = *(const uint4*)(smem + kb * U + r * 128 + (((lane ^ r) & 7) << 4));
          a = fmaf(bf_lo(u.x), bf_lo(v.x), a); a = fmaf(bf_hi(u.x), bf_hi(v.x), a);
          a = fmaf(bf_lo(u.y), bf_lo(v.y), a); a = fmaf(bf_hi(u.y), bf_hi(v.y), a);
          a = fmaf(bf_lo(u.z), bf_lo(v.z), a); a = fmaf(bf_hi(u.z), bf_hi(v.z), a);
          a = fmaf(bf_lo(u.w), bf_lo(v.w), a); a = fmaf(bf_hi(u.w), bf_hi(v.w), a);
        }
#pragma unroll
        for (int o = 4; o; o >>= 1) a += __shfl_xor_sync(0xffffffffu, a, o);
        if ((lane & 7) == 0)
          asm volatile("st.relaxed.gpu.global.f32 [%0], %1;" ::"l"(g_gate + rb * 128 + r), "f"(tagf(__fdividef(1.0f, 1.0f + __expf(-a)), tag)) : "memory");
        if (t == 0) PROF_EV(18);
      }
    };
    {
      const int g = lane >> 2, q = lane & 3;
      uint32_t wf[32];
      if (!helper) {
        gate_rows();
        const uint32_t wa = sb + OFF_T + w * (3072 + 4) + q * 48 + g * 2;
        auto w_issue = [&](const CUtensorMap* m) {
          if (lane == 0) { mbar_expect_tx(bars + 8 * (B_WR + w), 3072); tma4d(sb + OFF_T + w * 3072, m, bars + 8 * (B_WR + w), 16 * kg, 0, 2 * w, tn); }
          __syncwarp();
        };
        mbar_wait(bars + 8 * (B_FE + 3), 0);
        if (t == 0) PROF_EV(32);
        w_issue(&maps.wr);
#pragma unroll 1
        for (int ri = 0; ri < 2; ri++) {
          mbar_wait(bars + 8 * (B_WR + w), ri);
#pragma unroll
          for (int n2 = 0; n2 < 2; n2++) {
            uint32_t v[16];
#pragma unroll
            for (int i = 0; i < 16; i++)
              asm volatile("ld.shared.u16 %0, [%1];" : "=r"(v[i]) : "r"(wa + (4 * n2 + ((i >> 1) & 3)) * 192 + (i & 1) * (1536 + 2) + (i >> 3) * 16) : "memory");
#pragma unroll
            for (int i = 0; i < 16; i++) {
              uint32_t& d = wf[(i >> 3) * 16 + 8 * n2 + (i & 7)];
              d = __byte_perm(d, v[i], 0x5432);
              asm volatile("" : "+r"(d)::"memory");
            }
          }
          __syncwarp();
          if (ri == 0) w_issue(&maps.wi);
        }
        asm volatile("bar.sync 1, 128;" ::: "memory");
        if (t == 0) PROF_EV(11);
      } else {
        asm volatile("bar.sync 4, 256;" ::: "memory");
        hint_wait(&g_cntW[0], (ep + 1) * 128u);
        const uint32_t t0 = (uint32_t)clock();
#pragma unroll 1
        for (;;) {
          uint32_t bad = 0;
#pragma unroll
          for (int i = 0; i < 32; i++) {
            const float2 v = ld_x2((const float2*)g_Wh + (i >> 4) * 2048 + 16 * w + g + 8 * (i & 1) + 64 * q + ((i >> 1) & 7) * 256);
            wf[i] = __float_as_uint(v.x); bad |= __float_as_uint(v.y) ^ tag;
          }
          if (!__any_sync(0xffffffffu, bad & 1)) break;
          spin_guard(t0);
        }
        if (t == 0) PROF_EV(11);
      }
      if (t == 0) { mbar_expect_tx(bars + 8 * B_W, 8192); bulk_load(sb + OFF_D, g_DT.v, 8192, bars + 8 * B_W); }
      if (!helper) {
        const uint32_t t0 = (uint32_t)clock();
        uint32_t v;
        do { v = ld_x1(g_gate + rb * 128 + t); spin_guard(t0); } while (__any_sync(0xffffffffu, (v ^ tag) & 1));
        *(uint32_t*)(smem + OFF_G + t * 4) = v;
        __syncwarp();
        mbar_arrive_if(lane == 0, bars + 8 * B_G);
      }
      mbar_wait(bars + 8 * B_W, 0);
      mbar_wait(bars + 8 * B_HX, 0);
      if (t == 0) PROF_EV(12);
      const uint32_t dd = (sb & 0x3FFFF) >> 4;
      const uint64_t dF = d128((dd + (OFF_D >> 4)) | (512u << 16)), dI = d128((dd + (OFF_D >> 4)) | (1u << 16)), dA = d128((dd + (OFF_XB >> 4)) | (512u << 16));
      float az[32];
      const int zero = blockIdx.x >> 16;
      uint32_t pf[32];
#pragma unroll
      for (int mt = 0; mt < 2; mt++) {
        wg_fence();
        if (mt == 0) mma_ss64<0, 3, 0>(az, dA, dF);
        else mma_ss64<0, 3, 2>(az, dA + 512, dF, zero);
#pragma unroll
        for (int k = 1; k < 4; k++) mma_ss64<0, 3, 1>(az, dA + (mt * 512 + k * 128), dF + k * 128);
        wg_commit();
        wg_wait<0>();
        fence_regs<0, 32>(az);
#pragma unroll
        for (int i = 0; i < 16; i++) {
          const float wr = bf_lo(wf[16 * mt + i]), wi = bf_hi(wf[16 * mt + i]);
          pf[16 * mt + i] = pack_pin(fmaf(az[2 * i], wr, -az[2 * i + 1] * wi), fmaf(az[2 * i], wi, az[2 * i + 1] * wr));
        }
      }
      if (t == 0) PROF_EV(16);
#pragma unroll
      for (int mt = 0; mt < 2; mt++) {
        wg_fence();
        mma_rs64<0, 0, 2>(az, pf[16 * mt], pf[16 * mt + 1], pf[16 * mt + 2], pf[16 * mt + 3], dI, mt ? (int)helper : zero);
#pragma unroll
        for (int k = 1; k < 4; k++) mma_rs64<0, 0, 1>(az, pf[16 * mt + 4 * k], pf[16 * mt + 4 * k + 1], pf[16 * mt + 4 * k + 2], pf[16 * mt + 4 * k + 3], dI + k * 2);
        wg_commit();
        wg_wait<0>();
        fence_regs<0, 32>(az);
        if (!helper) {
          const int m = lane >> 3, r = lane & 7;
          const int sl = 2 * (m >> 1) + ((r >> 1) & 1) + 4 * (r >> 2);
          const uint32_t a0 = sb + OFF_XB + (2 * w + (m & 1)) * 2048 + sl * 64 + (((mt * 2 + (r & 1)) ^ (sl >> 1)) << 4);
#pragma unroll
          for (int i = 0; i < 4; i++)
            stsm4t(a0 + i * 512, pack_bf16(az[8 * i], az[8 * i + 1]), pack_bf16(az[8 * i + 2], az[8 * i + 3]), pack_bf16(az[8 * i + 4], az[8 * i + 5]),
                   pack_bf16(az[8 * i + 6], az[8 * i + 7]));
        }
      }
      if (helper) {
#pragma unroll
        for (int i = 0; i < 16; i++) {
          const int n = i >> 1, s0 = 8 * (n >> 1) + 2 * (n & 1) + (q & 1) + 4 * (q >> 1);
          if ((n & 1) == (int)(blockIdx.x & 1)) st_u2(g_Ts + s0 * 64 + 16 * w + g + 8 * (i & 1), pack_bf16(az[2 * i], az[2 * i + 1]), tag);
        }
        __syncwarp();
        hint_add_if(lane == 0, &g_cntH[0]);
        if (t == 0) { g_epoch[blockIdx.x * 8] = ep + 1; PROF_EV(13); }
      } else {
        asm volatile("fence.proxy.async.shared::cta;" ::: "memory");
        __syncwarp();
        if (lane == 0) {
          if (t == 0) PROF_EV(17);
          if (SPACE) __nanosleep(SPACE * w);
          asm volatile("cp.async.bulk.tensor.3d.global.shared::cta.bulk_group [%0, {%2, %3, %4}], [%1];" ::"l"(&maps.ts), "r"(sb + OFF_XB + w * 4096),
                       "r"(32 * kg), "r"(0), "r"(8 * tn + 2 * w) : "memory");
          bulk_done_signal(&g_cntT[32 * j]);
          if (t == 96) PROF_EV(13);
        }
        __syncwarp();
        if (j == 0) {
          hint_wait(&g_cntH[0], (ep + 1) * 8u);
          const uint32_t t0 = (uint32_t)clock();
          float2 v;
          do { v = ld_x2((const float2*)g_Ts + 2 * rb * 64 + t); spin_guard(t0); } while (__any_sync(0xffffffffu, (__float_as_uint(v.y) ^ tag) & 1));
          mbar_wait(bars + 8 * B_TL, 0);
          const uint32_t u = __float_as_uint(v.x);
          *(uint16_t*)(smem + OFF_T + t * 128 + ((t & 7) << 4)) = (uint16_t)u;
          *(uint16_t*)(smem + OFF_T + t * 128 + (((t & 7) ^ 1) << 4)) = (uint16_t)(u >> 16);
          asm volatile("fence.proxy.async.shared::cta;" ::: "memory");
          __syncwarp();
          mbar_arrive_if(lane == 0, bars + 8 * B_T);
        }
      }
    }
  } else {
    asm volatile("setmaxnreg.dec.sync.aligned.u32 24;");
    auto xf_load = [&](int q) {
      const uint32_t fb = bars + 8 * (B_FX + q);
      mbar_expect_tx(fb, U + 8192);
      tma3d(sb + q * U, &maps.x, fb, 64 * q, 0, 2 * rb);
      if (q >= 4) mbar_wait(bars + 8 * (B_FE + ((q - 4) >> 1)), 0);
      tma2d(sb + OFF_XB + (q & 3) * 8192, &maps.ft, fb, 64 * q, 64 * j);
    };
    if (lane == 0) {
      if (warp == 14) {
#pragma unroll
        for (int i = 0; i < B_FT; i++) mbar_init(bars + 8 * i, 1);
        asm volatile("fence.proxy.async.shared::cta;" ::: "memory");
        if (!helper) {
#pragma unroll 1
          for (int n = 0; n < 2; n++) {
            const uint32_t fb = bars + 8 * (B_FA + n);
            xf_load(2 * n); xf_load(2 * n + 1);
            mbar_expect_tx(fb, U);
            tma2d(sb + OFF_RING + n * U, &maps.g64, fb, f_full, 64 * n);
            tma2d(sb + OFF_RING + n * U + 8192, &maps.u64, fb, f_full, 64 * n);
          }
        }
      } else if (warp == 15) {
#pragma unroll
        for (int i = B_FT; i < NBAR; i++) mbar_init(bars + 8 * i, i < B_EA ? 1 : i < B_T ? 2 : 4);
#pragma unroll
        for (int i = 0; i < 4; i++) mbar_expect_tx(bars + 8 * (B_Z + i), U);
        asm volatile("fence.mbarrier_init.release.cluster;" ::: "memory");
        asm volatile("fence.proxy.async.shared::cta;" ::: "memory");
      } else if (warp == 13) {
#pragma unroll
        for (int i = 1; i < 4; i++) asm volatile("prefetch.tensormap [%0];" ::"l"((const char*)&maps + i * 128) : "memory");
      }
    }
    __syncwarp();
    asm volatile("bar.arrive 0, 384;" ::: "memory");
    asm volatile("bar.arrive 4, 256;" ::: "memory");
    __syncwarp();
    asm volatile("barrier.cluster.arrive.relaxed.aligned;" ::: "memory");
    asm volatile("bar.sync 3, 128;" ::: "memory");
    if (warp == 15 && !helper) {
        mbar_wait(bars + 8 * B_FE, 0);
        const uint32_t tag = (ld_x1(&g_epoch[blockIdx.x * 8]) + 1) & 1;
        const int c = lane >> 4, jj = 16 * blockIdx.x + (lane & 15), jm = (2048 - jj) & 2047;
        const unsigned short* pr = (const unsigned short*)w_r + 256 * c;
        const unsigned short* pi = (const unsigned short*)w_i + 256 * c;
        const float wr = 0.25f * (bf_lo(__ldg(pr + jj * 257)) + bf_lo(__ldg(pr + jm * 257)));
        const float wi = 0.25f * (bf_lo(__ldg(pi + jj * 257)) - bf_lo(__ldg(pi + jm * 257)));
        st_u2(g_Wh + c * 2048 + jj, c ? pack_bf16(-wi, wr) : pack_bf16(wr, wi), tag);
        __syncwarp();
        hint_add_if(lane == 0, &g_cntW[0]);
      }
    if (lane == 0 && (!helper || warp == 15)) {
      if (warp < 14) {
        const int p = warp - 12;
#pragma unroll 1
        for (int n = 2; n < 31; n++) {
          const bool table = n == 4 || n >= 29;
          const int q = n < 4 ? n : n - 1;
          const CUtensorMap* m = table ? &maps.e : n >= 25 ? &maps.g32 + p : &maps.g64 + p;
          const int c0 = table ? 0 : n >= 25 ? f_half : f_full + 64 * (q >> 3);
          const int c1 = table ? (2 * rb + ((n & 1) ^ 1)) * 128 + 64 * p : n >= 25 ? 128 * (n - 25) : 64 * (q & 7);
          const uint32_t fb = bars + 8 * (B_FA + (n & 3)), dst = sb + OFF_RING + (n & 3) * U + p * 8192;
          if (n < 4) mbar_wait(bars + 8 * (B_FE + n - 2), 0);
          else mbar_wait(bars + 8 * (B_EA + (n & 3)), ((n >> 2) & 1) ^ 1);
          tma2d(dst, m, fb, c0, c1);
          if (p == 0) mbar_expect_tx(fb, U);
        }
      } else if (warp == 15) {
        const unsigned ep1 = ld_x1(&g_epoch[blockIdx.x * 8]) + 1;
        flag_wait(&g_cntX[helper ? 0 : 32 * j], ep1 * 16u);
        PROF_EV(22);
        mbar_expect_tx(bars + 8 * B_HX, U);
        bulk_load(sb + OFF_XB, g_X + (size_t)(helper ? 128 : kg * 8 + tn) * 8192, U, bars + 8 * B_HX);
        if (!helper) {
          flag_wait(&g_cntT[32 * j], ep1 * 64u);
          PROF_EV(23);
          mbar_expect_tx(bars + 8 * B_TL, U);
          tma3d(sb + OFF_T, &maps.t, bars + 8 * B_TL, 64 * j, 0, 2 * rb);
#pragma unroll 1
          for (int i = 0; i < 3; i++) {
            mbar_wait(bars + 8 * (B_PZ + (i >> 1)), 0);
            flag_wait(&g_cntP[32 * (rb * 8 + j) + i], ep1 * 8u);
            mbar_expect_tx(bars + 8 * (B_HP + i), U);
            bulk_load(sb + i * U, g_part + (size_t)((rb * 8 + j) * 3 + i) * 1024, U, bars + 8 * (B_HP + i));
          }
          g_epoch[blockIdx.x * 8] = ep1;
        }
      } else {
#pragma unroll 1
        for (int q = 4; q < 8; q++) xf_load(q);
        mbar_wait(bars + 8 * (B_FE + 2), 0);
        mbar_expect_tx(bars + 8 * B_E0, U);
        tma2d(sb + OFF_XB, &maps.e, bars + 8 * B_E0, 0, 2 * rb * 128);
        tma2d(sb + OFF_XB + 8192, &maps.e, bars + 8 * B_E0, 0, 2 * rb * 128 + 64);
#pragma unroll 1
        for (int h2 = 0; h2 < 2; h2++) {
          const int s0 = 2 * rb + h2, sg = (s0 & ~6) | ((s0 & 2) << 1) | ((s0 & 4) >> 1);
          mbar_wait(bars + 8 * (B_XS + h2), 0);
#pragma unroll 1
          for (int c = 0; c < 2; c++) {
            asm volatile("cp.async.bulk.tensor.4d.global.shared::cta.bulk_group [%0, {%2, %3, %4, %5}], [%1];" ::"l"(&maps.xs),
                         "r"(sb + OFF_XB + h2 * 8192 + c * 4096), "r"(0), "r"(sg), "r"(0), "r"(16 * j + 8 * c) : "memory");
            if (j == 0)
              asm volatile("cp.async.bulk.global.shared::cta.bulk_group [%0], [%1], 256;" ::"l"(g_X + 128 * 8192 + c * 4096 + sg * 128),
                           "r"(sb + OFF_SP + h2 * 512 + c * 256) : "memory");
            if (SPACE && h2 + c < 2) __nanosleep(SPACE);
          }
        }
        bulk_done_signal(&g_cntX[32 * j]);
        PROF_EV(20);
#pragma unroll 1
        for (int t = 0; t < 8; t++) {
          const int i = t < 3 ? t + 1 : t < 6 ? t - 2 : 0;
          const int col = 64 * (2 * ((q4 + i) & 3) + ((t < 3 || t == 6) ? 1 - rank : rank));
          const uint32_t fb = bars + 8 * (B_FT + (t & 3)), dst = sb + (t & 3) * TB;
          mbar_wait(bars + 8 * (B_ET + (t == 2 ? 3 : t & 3)), t >> 2);
          mbar_expect_tx(fb, TB);
          tma2d(dst, &maps.d224, fb, col, 224 * j);
          if (t < 2) mbar_wait(bars + 8 * (B_ET + t + 1), 0);
          tma2d(dst + 28672, &maps.ft, fb, col, 64 * j);
        }
      }
    }
  }
}

typedef CUresult (*EncodeFn)(CUtensorMap*, CUtensorMapDataType, cuuint32_t, void*, const cuuint64_t*, const cuuint64_t*, const cuuint32_t*,
                             const cuuint32_t*, CUtensorMapInterleave, CUtensorMapSwizzle, CUtensorMapL2promotion, CUtensorMapFloatOOBfill);

static void encode(EncodeFn f, CUtensorMap* m, const void* base, int rank, const cuuint64_t* dims, const cuuint64_t* strides, const cuuint32_t* box,
                   CUtensorMapSwizzle sw) {
  cuuint32_t es[5] = {1, 1, 1, 1, 1};
  f(m, CU_TENSOR_MAP_DATA_TYPE_BFLOAT16, rank, (void*)base, dims, strides, box, es, CU_TENSOR_MAP_INTERLEAVE_NONE, sw,
    CU_TENSOR_MAP_L2_PROMOTION_L2_128B, CU_TENSOR_MAP_FLOAT_OOB_FILL_NONE);
}

extern "C" void kernel_launch(void* const* d_in, const int* in_sizes, int n_in, void* d_out, int out_size) {
  (void)in_sizes; (void)n_in; (void)out_size;
  const __nv_bfloat16* x = (const __nv_bfloat16*)d_in[0];
  const __nv_bfloat16* w_r = (const __nv_bfloat16*)d_in[1];
  const __nv_bfloat16* w_i = (const __nv_bfloat16*)d_in[2];
  const __nv_bfloat16* Wg = (const __nv_bfloat16*)d_in[4];
  const __nv_bfloat16* Wu = (const __nv_bfloat16*)d_in[5];
  const __nv_bfloat16* Wd = (const __nv_bfloat16*)d_in[6];
  const __nv_bfloat16* gw = (const __nv_bfloat16*)d_in[7];

  void* fp = nullptr; cudaDriverEntryPointQueryResult qr;
  cudaGetDriverEntryPoint("cuTensorMapEncodeTiled", &fp, cudaEnableDefault, &qr);
  EncodeFn enc = (EncodeFn)fp;
  void *pFT, *pET, *pX, *pT;
  cudaGetSymbolAddress(&pX, g_X); cudaGetSymbolAddress(&pT, g_T);
  cudaGetSymbolAddress(&pFT, g_FT); cudaGetSymbolAddress(&pET, g_ET);

  Maps mp;
  const CUtensorMapSwizzle S128 = CU_TENSOR_MAP_SWIZZLE_128B, S64 = CU_TENSOR_MAP_SWIZZLE_64B;
  { cuuint64_t d[3] = {512, 64, 32}, s[2] = {32768, 1024}; cuuint32_t b[3] = {64, 64, 2}; encode(enc, &mp.x, x, 3, d, s, b, S128); }
  { cuuint64_t d[2] = {512, 512}, s[1] = {1024}; cuuint32_t b[2] = {64, 64}; encode(enc, &mp.ft, pFT, 2, d, s, b, S128); }
  { cuuint64_t d[4] = {128, 32, 2, 129}, s[3] = {256, 8192, 16384}; cuuint32_t b[4] = {128, 1, 2, 8}; encode(enc, &mp.xs, pX, 4, d, s, b, CU_TENSOR_MAP_SWIZZLE_NONE); }
  { cuuint64_t d[3] = {512, 32, 64}, s[2] = {65536, 1024}; cuuint32_t b[3] = {32, 32, 2}; encode(enc, &mp.ts, pT, 3, d, s, b, S64); }
  { cuuint64_t d[3] = {512, 64, 32}, s[2] = {1024, 65536}; cuuint32_t b[3] = {64, 64, 2}; encode(enc, &mp.t, pT, 3, d, s, b, S128); }
  { cuuint64_t d[2] = {64, 4096}, s[1] = {128}; cuuint32_t b[2] = {64, 64}; encode(enc, &mp.e, pET, 2, d, s, b, S128); }
  { cuuint64_t d[2] = {1792, 512}, s[1] = {3584}; cuuint32_t b[2] = {64, 64}, b2[2] = {32, 128};
    encode(enc, &mp.g64, Wg, 2, d, s, b, S128); encode(enc, &mp.u64, Wu, 2, d, s, b, S128);
    encode(enc, &mp.g32, Wg, 2, d, s, b2, S64); encode(enc, &mp.u32, Wu, 2, d, s, b2, S64); }
  { cuuint64_t d[2] = {512, 1792}, s[1] = {1024}; cuuint32_t b[2] = {64, 224}; encode(enc, &mp.d224, Wd, 2, d, s, b, S128); }
  { cuuint64_t d[4] = {264, 32, 8, 8}, s[3] = {32896, 512, 4112}; cuuint32_t b[4] = {24, 32, 2, 1};
    encode(enc, &mp.wr, w_r, 4, d, s, b, CU_TENSOR_MAP_SWIZZLE_NONE); encode(enc, &mp.wi, w_i, 4, d, s, b, CU_TENSOR_MAP_SWIZZLE_NONE); }

  cudaFuncSetAttribute(fused_kernel, cudaFuncAttributeMaxDynamicSharedMemorySize, SMEM_BYTES);
  fused_kernel<<<NCTA, 512, SMEM_BYTES>>>(mp, w_r, w_i, gw, (__nv_bfloat16*)d_out);
}
```

```cpp
#include <cuda_runtime.h>
#include <cuda_bf16.h>
#include <cuda.h>
#include <stdint.h>

namespace tbl {
constexpr double PI = 3.14159265358979323846264338327950288;
constexpr double sin_s(double x) { double t = x, s = x; for (int n = 1; n < 12; n++) { t *= -x * x / ((2 * n) * (2 * n + 1)); s += t; } return s; }
constexpr double cos_s(double x) { double t = 1, s = 1; for (int n = 1; n < 12; n++) { t *= -x * x / ((2 * n - 1) * (2 * n)); s += t; } return s; }
constexpr double cos2048(int m) {
  m &= 2047; if (m > 1024) m = 2048 - m;
  bool neg = false; if (m > 512) { m = 1024 - m; neg = true; }
  double v = (m <= 256) ? cos_s(2 * PI * m / 2048) : sin_s(2 * PI * (512 - m) / 2048);
  return neg ? -v : v;
}
constexpr uint16_t to_bf16(double v) {
  if (v == 0) return 0;
  uint16_t s = 0; if (v < 0) { s = 0x8000; v = -v; }
  int e = 0; while (v >= 2) { v /= 2; e++; } while (v < 1) { v *= 2; e--; }
  double m = (v - 1) * 128; int mi = (int)m; double fr = m - mi;
  if (fr > 0.5 || (fr == 0.5 && (mi & 1))) mi++;
  if (mi == 128) { mi = 0; e++; }
  return (uint16_t)(s | ((e + 127) << 7) | mi);
}
struct CosT { uint16_t v[2048]; constexpr CosT() : v() { for (int i = 0; i < 2048; i++) v[i] = to_bf16(cos2048(i)); } };
struct alignas(1024) FT {
  uint16_t v[512 * 512];
  constexpr FT() : v() {
    CosT c;
    for (int r = 0; r < 512; r++) {
      int k = (r >> 4) * 8 + (r & 7), e = (r >> 3) & 1;
      int mul = 4 * k, add = e ? 512 : 0;
      if (k == 0 && e == 1) { mul = 1024; add = 0; }
      for (int d = 0; d < 512; d++) v[r * 512 + d] = c.v[(d * mul + add) & 2047];
    }
  }
};
struct alignas(1024) ET {
  uint16_t v[2048 * 128];
  constexpr ET() : v() {
    CosT c;
    for (int s = 0; s < 2048; s++)
      for (int j = 0; j < 64; j++) {
        const int o = (s & 31) * 8192 + (s >> 5) * 64 + j;
        v[o] = c.v[(s * j) & 2047]; v[o + 4096] = c.v[(s * j + 512) & 2047];
      }
  }
};
struct alignas(1024) DT {
  uint16_t v[64 * 64];
  constexpr DT() : v() {
    CosT c;
    for (int r = 0; r < 64; r++)
      for (int n = 0; n < 64; n++) {
        const int sg = r >> 1, s0 = (sg & ~6) | ((sg & 2) << 1) | ((sg & 4) >> 1), e = r & 1, f = n & 1;
        const int m = 64 * s0 * (n >> 1) + (e == f ? 0 : e ? -512 : 512);
        v[r * 64 + (((n >> 3) ^ (r & 7)) << 3) + (n & 7)] = c.v[m & 2047];
      }
  }
};
}

__device__ constexpr tbl::FT g_FT = tbl::FT();
__device__ constexpr tbl::ET g_ET = tbl::ET();
__device__ constexpr tbl::DT g_DT = tbl::DT();

__device__ __align__(1024) uint16_t g_X[129 * 8192];
__device__ __align__(1024) uint16_t g_T[32 * 64 * 512];
__device__ __align__(1024) uint2 g_Ts[32 * 64];
__device__ __align__(1024) uint4 g_part[128 * 3 * 1024];
__device__ __align__(16) float g_gate[16 * 128];
__device__ __align__(16) uint2 g_Wh[2 * 2048];
__device__ unsigned g_epoch[132 * 8];
__device__ unsigned g_cntX[8 * 32], g_cntT[8 * 32], g_cntP[128 * 32], g_cntW[32], g_cntH[32];
#define PROF_EV(i) do {} while (0)
#define PROF_CK(i) do {} while (0)

__device__ __forceinline__ uint32_t smem_u32(const void* p) { return (uint32_t)__cvta_generic_to_shared(p); }
__device__ __forceinline__ void mbar_init(uint32_t bar, uint32_t cnt) { asm volatile("mbarrier.init.shared::cta.b64 [%0], %1;" ::"r"(bar), "r"(cnt)); }
__device__ __forceinline__ void mbar_expect_tx(uint32_t bar, uint32_t bytes) { asm volatile("mbarrier.arrive.expect_tx.shared::cta.b64 _, [%0], %1;" ::"r"(bar), "r"(bytes) : "memory"); }
__device__ __forceinline__ void mbar_arrive(uint32_t bar) { asm volatile("mbarrier.arrive.shared::cta.b64 _, [%0];" ::"r"(bar) : "memory"); }
__device__ __forceinline__ void mbar_arrive_if(bool p, uint32_t bar) {
  asm volatile("{\n.reg .pred p;\nsetp.ne.b32 p, %1, 0;\n@p mbarrier.arrive.shared::cta.b64 _, [%0];\n}" ::"r"(bar), "r"((int)p) : "memory");
}
__device__ __forceinline__ void hint_add_if(bool p, unsigned* a) {
  asm volatile("{\n.reg .pred p;\nsetp.ne.b32 p, %1, 0;\n@p red.relaxed.gpu.global.add.u32 [%0], 1;\n}" ::"l"(a), "r"((int)p) : "memory");
}
__device__ __forceinline__ bool mbar_try(uint32_t bar, uint32_t parity) {
  uint32_t ok;
  asm volatile("{\n.reg .pred p;\nmbarrier.test_wait.parity.shared::cta.b64 p, [%1], %2;\nselp.u32 %0, 1, 0, p;\n}" : "=r"(ok) : "r"(bar), "r"(parity) : "memory");
  return ok;
}
__device__ __forceinline__ void mbar_wait(uint32_t bar, uint32_t parity) {
  asm volatile(
      "{\n.reg .pred p;\n.reg .u32 n;\nmov.u32 n, 0;\n"
      "W_LOOP:\nmbarrier.try_wait.parity.shared::cta.b64 p, [%0], %1;\n@p bra W_DONE;\n"
      "add.u32 n, n, 1;\nsetp.lt.u32 p, n, 0x40000;\n@p bra W_LOOP;\ntrap;\nW_DONE:\n}" ::"r"(bar), "r"(parity) : "memory");
}
__device__ __forceinline__ void bulk_load(uint32_t dst, const void* src, uint32_t bytes, uint32_t bar) {
  asm volatile("cp.async.bulk.shared::cluster.global.mbarrier::complete_tx::bytes [%0], [%1], %2, [%3];" ::"r"(dst), "l"(src), "r"(bytes), "r"(bar) : "memory");
}
__device__ __forceinline__ void cp16(uint32_t dst, const void* src) { asm volatile("cp.async.cg.shared.global [%0], [%1], 16;" ::"r"(dst), "l"(src) : "memory"); }
__device__ __forceinline__ void spin_guard(uint32_t t0) { if ((uint32_t)clock() - t0 > (1u << 30)) __trap(); }
__device__ __forceinline__ float tagf(float v, uint32_t tag) { return __uint_as_float((__float_as_uint(v) & ~1u) | tag); }
__device__ __forceinline__ float untag(float v) { return __uint_as_float(__float_as_uint(v) & ~1u); }
__device__ __forceinline__ void st_x2(float2* p, float a, float b) { asm volatile("st.relaxed.gpu.global.v2.f32 [%0], {%1,%2};" ::"l"(p), "f"(a), "f"(b) : "memory"); }
__device__ __forceinline__ float2 ld_x2(const float2* p) { float2 v; asm volatile("ld.relaxed.gpu.global.v2.f32 {%0,%1}, [%2];" : "=f"(v.x), "=f"(v.y) : "l"(p) : "memory"); return v; }
__device__ __forceinline__ void st_u2(uint2* p, uint32_t a, uint32_t b) { asm volatile("st.relaxed.gpu.global.v2.u32 [%0], {%1,%2};" ::"l"(p), "r"(a), "r"(b) : "memory"); }
__device__ __forceinline__ void prefetch2d(const CUtensorMap* m, int c0, int c1) { asm volatile("cp.async.bulk.prefetch.tensor.2d.L2.global [%0, {%1, %2}];" ::"l"(m), "r"(c0), "r"(c1) : "memory"); }
__device__ __forceinline__ void prefetch1d(const void* p, uint32_t bytes) { asm volatile("cp.async.bulk.prefetch.L2.global [%0], %1;" ::"l"(p), "r"(bytes) : "memory"); }
__device__ __forceinline__ uint32_t ld_x1(const void* p) { uint32_t v; asm volatile("ld.relaxed.gpu.global.u32 %0, [%1];" : "=r"(v) : "l"(p) : "memory"); return v; }
__device__ __forceinline__ uint4 ld_x4(const void* p) { uint4 v; asm volatile("ld.relaxed.gpu.global.v4.u32 {%0,%1,%2,%3}, [%4];" : "=r"(v.x), "=r"(v.y), "=r"(v.z), "=r"(v.w) : "l"(p) : "memory"); return v; }
__device__ __forceinline__ void st_x4(void* p, uint32_t a, uint32_t b, uint32_t c, uint32_t d) { asm volatile("st.relaxed.gpu.global.v4.u32 [%0], {%1,%2,%3,%4};" ::"l"(p), "r"(a), "r"(b), "r"(c), "r"(d) : "memory"); }
__device__ __forceinline__ uint32_t mapa(uint32_t a, uint32_t cta) { uint32_t r; asm volatile("mapa.shared::cluster.u32 %0, %1, %2;" : "=r"(r) : "r"(a), "r"(cta)); return r; }
__device__ __forceinline__ void stsm4t(uint32_t a, uint32_t r0, uint32_t r1, uint32_t r2, uint32_t r3) {
  asm volatile("stmatrix.sync.aligned.m8n8.x4.trans.shared.b16 [%0], {%1,%2,%3,%4};" ::"r"(a), "r"(r0), "r"(r1), "r"(r2), "r"(r3) : "memory");
}
__device__ __forceinline__ void hint_add(unsigned* p) { asm volatile("red.relaxed.gpu.global.add.u32 [%0], 1;" ::"l"(p) : "memory"); }
__device__ __forceinline__ void hint_wait(const unsigned* p, unsigned target) {
  const uint32_t t0 = (uint32_t)clock();
  while ((int)(ld_x1(p) - target) < 0) spin_guard(t0);
}
__device__ __forceinline__ void bulk_done_signal(unsigned* p) {
  asm volatile("cp.async.bulk.commit_group;\ncp.async.bulk.wait_group 0;\nfence.proxy.async.global;" ::: "memory");
  hint_add(p);
}
__device__ __forceinline__ void flag_wait(const unsigned* p, unsigned target) {
  hint_wait(p, target);
  asm volatile("fence.proxy.async.global;" ::: "memory");
}
__device__ __forceinline__ void tma2d(uint32_t dst, const CUtensorMap* m, uint32_t bar, int c0, int c1) {
  asm volatile("cp.async.bulk.tensor.2d.shared::cluster.global.mbarrier::complete_tx::bytes [%0], [%1, {%3, %4}], [%2];" ::"r"(dst), "l"(m), "r"(bar), "r"(c0), "r"(c1) : "memory");
}
__device__ __forceinline__ void tma3d(uint32_t dst, const CUtensorMap* m, uint32_t bar, int c0, int c1, int c2) {
  asm volatile("cp.async.bulk.tensor.3d.shared::cluster.global.mbarrier::complete_tx::bytes [%0], [%1, {%3, %4, %5}], [%2];" ::"r"(dst), "l"(m), "r"(bar), "r"(c0), "r"(c1), "r"(c2) : "memory");
}
__device__ __forceinline__ void tma4d(uint32_t dst, const CUtensorMap* m, uint32_t bar, int c0, int c1, int c2, int c3) {
  asm volatile("cp.async.bulk.tensor.4d.shared::cluster.global.mbarrier::complete_tx::bytes [%0], [%1, {%3, %4, %5, %6}], [%2];" ::"r"(dst), "l"(m), "r"(bar), "r"(c0), "r"(c1), "r"(c2), "r"(c3) : "memory");
}
__device__ __forceinline__ void wg_fence() { asm volatile("wgmma.fence.sync.aligned;" ::: "memory"); }
__device__ __forceinline__ void wg_commit() { asm volatile("wgmma.commit_group.sync.aligned;" ::: "memory"); }
template <int N> __device__ __forceinline__ void wg_wait() { asm volatile("wgmma.wait_group.sync.aligned %0;" ::"n"(N) : "memory"); }
template <int O, int N, int NN> __device__ __forceinline__ void fence_regs(float (&d)[NN]) {
#pragma unroll
  for (int i = 0; i < N; i++) asm volatile("" : "+f"(d[O + i])::"memory");
}
__device__ __forceinline__ uint32_t pack_bf16(float lo, float hi) {
  uint32_t r; asm("cvt.rn.bf16x2.f32 %0, %1, %2;" : "=r"(r) : "f"(hi), "f"(lo)); return r;
}
__device__ __forceinline__ uint32_t pack_pin(float lo, float hi) {
  uint32_t r; asm volatile("cvt.rn.bf16x2.f32 %0, %1, %2;" : "=r"(r) : "f"(hi), "f"(lo) : "memory"); return r;
}
__device__ __forceinline__ float bf_lo(uint32_t u) { return __uint_as_float(u << 16); }
__device__ __forceinline__ float bf_hi(uint32_t u) { return __uint_as_float(u & 0xffff0000u); }

__device__ __forceinline__ uint64_t d128(uint32_t lo) { uint64_t d; asm("mov.b64 %0, {%1, 0x40000040};" : "=l"(d) : "r"(lo)); return d; }
__device__ __forceinline__ uint64_t d64(uint32_t lo) { uint64_t d; asm("mov.b64 %0, {%1, 0x80000020};" : "=l"(d) : "r"(lo)); return d; }
template<int O,int TB,int ACC,int NN> __device__ __forceinline__ void mma_ss64(float (&d)[NN], uint64_t da, uint64_t db, int sd = 0){
  if constexpr (ACC == 1) asm volatile("wgmma.mma_async.sync.aligned.m64n64k16.f32.bf16.bf16 {%0,%1,%2,%3,%4,%5,%6,%7,%8,%9,%10,%11,%12,%13,%14,%15,%16,%17,%18,%19,%20,%21,%22,%23,%24,%25,%26,%27,%28,%29,%30,%31}, %32, %33, 1, 1, 1, %35, %34;"
   : "+f"(d[O+0]), "+f"(d[O+1]), "+f"(d[O+2]), "+f"(d[O+3]), "+f"(d[O+4]), "+f"(d[O+5]), "+f"(d[O+6]), "+f"(d[O+7]), "+f"(d[O+8]), "+f"(d[O+9]), "+f"(d[O+10]), "+f"(d[O+11]), "+f"(d[O+12]), "+f"(d[O+13]), "+f"(d[O+14]), "+f"(d[O+15]), "+f"(d[O+16]), "+f"(d[O+17]), "+f"(d[O+18]), "+f"(d[O+19]), "+f"(d[O+20]), "+f"(d[O+21]), "+f"(d[O+22]), "+f"(d[O+23]), "+f"(d[O+24]), "+f"(d[O+25]), "+f"(d[O+26]), "+f"(d[O+27]), "+f"(d[O+28]), "+f"(d[O+29]), "+f"(d[O+30]), "+f"(d[O+31])
   : "l"(da), "l"(db), "n"(TB & 1), "n"(TB >> 1));
  else if constexpr (ACC == 0) asm volatile("wgmma.mma_async.sync.aligned.m64n64k16.f32.bf16.bf16 {%0,%1,%2,%3,%4,%5,%6,%7,%8,%9,%10,%11,%12,%13,%14,%15,%16,%17,%18,%19,%20,%21,%22,%23,%24,%25,%26,%27,%28,%29,%30,%31}, %32, %33, 0, 1, 1, %35, %34;"
   : "=f"(d[O+0]), "=f"(d[O+1]), "=f"(d[O+2]), "=f"(d[O+3]), "=f"(d[O+4]), "=f"(d[O+5]), "=f"(d[O+6]), "=f"(d[O+7]), "=f"(d[O+8]), "=f"(d[O+9]), "=f"(d[O+10]), "=f"(d[O+11]), "=f"(d[O+12]), "=f"(d[O+13]), "=f"(d[O+14]), "=f"(d[O+15]), "=f"(d[O+16]), "=f"(d[O+17]), "=f"(d[O+18]), "=f"(d[O+19]), "=f"(d[O+20]), "=f"(d[O+21]), "=f"(d[O+22]), "=f"(d[O+23]), "=f"(d[O+24]), "=f"(d[O+25]), "=f"(d[O+26]), "=f"(d[O+27]), "=f"(d[O+28]), "=f"(d[O+29]), "=f"(d[O+30]), "=f"(d[O+31])
   : "l"(da), "l"(db), "n"(TB & 1), "n"(TB >> 1));
  else asm volatile("{\n.reg .pred p;\nsetp.ne.b32 p, %36, 0;\nwgmma.mma_async.sync.aligned.m64n64k16.f32.bf16.bf16 {%0,%1,%2,%3,%4,%5,%6,%7,%8,%9,%10,%11,%12,%13,%14,%15,%16,%17,%18,%19,%20,%21,%22,%23,%24,%25,%26,%27,%28,%29,%30,%31}, %32, %33, p, 1, 1, %35, %34;\n}"
   : "+f"(d[O+0]), "+f"(d[O+1]), "+f"(d[O+2]), "+f"(d[O+3]), "+f"(d[O+4]), "+f"(d[O+5]), "+f"(d[O+6]), "+f"(d[O+7]), "+f"(d[O+8]), "+f"(d[O+9]), "+f"(d[O+10]), "+f"(d[O+11]), "+f"(d[O+12]), "+f"(d[O+13]), "+f"(d[O+14]), "+f"(d[O+15]), "+f"(d[O+16]), "+f"(d[O+17]), "+f"(d[O+18]), "+f"(d[O+19]), "+f"(d[O+20]), "+f"(d[O+21]), "+f"(d[O+22]), "+f"(d[O+23]), "+f"(d[O+24]), "+f"(d[O+25]), "+f"(d[O+26]), "+f"(d[O+27]), "+f"(d[O+28]), "+f"(d[O+29]), "+f"(d[O+30]), "+f"(d[O+31])
   : "l"(da), "l"(db), "n"(TB & 1), "n"(TB >> 1), "r"(sd));
}
template<int O,int TB,int ACC,int NN> __device__ __forceinline__ void mma_rs64(float (&d)[NN], uint32_t a0, uint32_t a1, uint32_t a2, uint32_t a3, uint64_t db, int sd = 0){
  if constexpr (ACC == 1) asm volatile("wgmma.mma_async.sync.aligned.m64n64k16.f32.bf16.bf16 {%0,%1,%2,%3,%4,%5,%6,%7,%8,%9,%10,%11,%12,%13,%14,%15,%16,%17,%18,%19,%20,%21,%22,%23,%24,%25,%26,%27,%28,%29,%30,%31}, {%32,%33,%34,%35}, %36, 1, 1, 1, %37;"
   : "+f"(d[O+0]), "+f"(d[O+1]), "+f"(d[O+2]), "+f"(d[O+3]), "+f"(d[O+4]), "+f"(d[O+5]), "+f"(d[O+6]), "+f"(d[O+7]), "+f"(d[O+8]), "+f"(d[O+9]), "+f"(d[O+10]), "+f"(d[O+11]), "+f"(d[O+12]), "+f"(d[O+13]), "+f"(d[O+14]), "+f"(d[O+15]), "+f"(d[O+16]), "+f"(d[O+17]), "+f"(d[O+18]), "+f"(d[O+19]), "+f"(d[O+20]), "+f"(d[O+21]), "+f"(d[O+22]), "+f"(d[O+23]), "+f"(d[O+24]), "+f"(d[O+25]), "+f"(d[O+26]), "+f"(d[O+27]), "+f"(d[O+28]), "+f"(d[O+29]), "+f"(d[O+30]), "+f"(d[O+31])
   : "r"(a0), "r"(a1), "r"(a2), "r"(a3), "l"(db), "n"(TB));
  else if constexpr (ACC == 0) asm volatile("wgmma.mma_async.sync.aligned.m64n64k16.f32.bf16.bf16 {%0,%1,%2,%3,%4,%5,%6,%7,%8,%9,%10,%11,%12,%13,%14,%15,%16,%17,%18,%19,%20,%21,%22,%23,%24,%25,%26,%27,%28,%29,%30,%31}, {%32,%33,%34,%35}, %36, 0, 1, 1, %37;"
   : "=f"(d[O+0]), "=f"(d[O+1]), "=f"(d[O+2]), "=f"(d[O+3]), "=f"(d[O+4]), "=f"(d[O+5]), "=f"(d[O+6]), "=f"(d[O+7]), "=f"(d[O+8]), "=f"(d[O+9]), "=f"(d[O+10]), "=f"(d[O+11]), "=f"(d[O+12]), "=f"(d[O+13]), "=f"(d[O+14]), "=f"(d[O+15]), "=f"(d[O+16]), "=f"(d[O+17]), "=f"(d[O+18]), "=f"(d[O+19]), "=f"(d[O+20]), "=f"(d[O+21]), "=f"(d[O+22]), "=f"(d[O+23]), "=f"(d[O+24]), "=f"(d[O+25]), "=f"(d[O+26]), "=f"(d[O+27]), "=f"(d[O+28]), "=f"(d[O+29]), "=f"(d[O+30]), "=f"(d[O+31])
   : "r"(a0), "r"(a1), "r"(a2), "r"(a3), "l"(db), "n"(TB));
  else asm volatile("{\n.reg .pred p;\nsetp.ne.b32 p, %38, 0;\nwgmma.mma_async.sync.aligned.m64n64k16.f32.bf16.bf16 {%0,%1,%2,%3,%4,%5,%6,%7,%8,%9,%10,%11,%12,%13,%14,%15,%16,%17,%18,%19,%20,%21,%22,%23,%24,%25,%26,%27,%28,%29,%30,%31}, {%32,%33,%34,%35}, %36, p, 1, 1, %37;\n}"
   : "+f"(d[O+0]), "+f"(d[O+1]), "+f"(d[O+2]), "+f"(d[O+3]), "+f"(d[O+4]), "+f"(d[O+5]), "+f"(d[O+6]), "+f"(d[O+7]), "+f"(d[O+8]), "+f"(d[O+9]), "+f"(d[O+10]), "+f"(d[O+11]), "+f"(d[O+12]), "+f"(d[O+13]), "+f"(d[O+14]), "+f"(d[O+15]), "+f"(d[O+16]), "+f"(d[O+17]), "+f"(d[O+18]), "+f"(d[O+19]), "+f"(d[O+20]), "+f"(d[O+21]), "+f"(d[O+22]), "+f"(d[O+23]), "+f"(d[O+24]), "+f"(d[O+25]), "+f"(d[O+26]), "+f"(d[O+27]), "+f"(d[O+28]), "+f"(d[O+29]), "+f"(d[O+30]), "+f"(d[O+31])
   : "r"(a0), "r"(a1), "r"(a2), "r"(a3), "l"(db), "n"(TB), "r"(sd));
}
template<int O,int TB,int ACC,int NN> __device__ __forceinline__ void mma_ss128(float (&d)[NN], uint64_t da, uint64_t db, int sd = 0){
  if constexpr (ACC == 1) asm volatile("wgmma.mma_async.sync.aligned.m64n128k16.f32.bf16.bf16 {%0,%1,%2,%3,%4,%5,%6,%7,%8,%9,%10,%11,%12,%13,%14,%15,%16,%17,%18,%19,%20,%21,%22,%23,%24,%25,%26,%27,%28,%29,%30,%31,%32,%33,%34,%35,%36,%37,%38,%39,%40,%41,%42,%43,%44,%45,%46,%47,%48,%49,%50,%51,%52,%53,%54,%55,%56,%57,%58,%59,%60,%61,%62,%63}, %64, %65, 1, 1, 1, %67, %66;"
   : "+f"(d[O+0]), "+f"(d[O+1]), "+f"(d[O+2]), "+f"(d[O+3]), "+f"(d[O+4]), "+f"(d[O+5]), "+f"(d[O+6]), "+f"(d[O+7]), "+f"(d[O+8]), "+f"(d[O+9]), "+f"(d[O+10]), "+f"(d[O+11]), "+f"(d[O+12]), "+f"(d[O+13]), "+f"(d[O+14]), "+f"(d[O+15]), "+f"(d[O+16]), "+f"(d[O+17]), "+f"(d[O+18]), "+f"(d[O+19]), "+f"(d[O+20]), "+f"(d[O+21]), "+f"(d[O+22]), "+f"(d[O+23]), "+f"(d[O+24]), "+f"(d[O+25]), "+f"(d[O+26]), "+f"(d[O+27]), "+f"(d[O+28]), "+f"(d[O+29]), "+f"(d[O+30]), "+f"(d[O+31]), "+f"(d[O+32]), "+f"(d[O+33]), "+f"(d[O+34]), "+f"(d[O+35]), "+f"(d[O+36]), "+f"(d[O+37]), "+f"(d[O+38]), "+f"(d[O+39]), "+f"(d[O+40]), "+f"(d[O+41]), "+f"(d[O+42]), "+f"(d[O+43]), "+f"(d[O+44]), "+f"(d[O+45]), "+f"(d[O+46]), "+f"(d[O+47]), "+f"(d[O+48]), "+f"(d[O+49]), "+f"(d[O+50]), "+f"(d[O+51]), "+f"(d[O+52]), "+f"(d[O+53]), "+f"(d[O+54]), "+f"(d[O+55]), "+f"(d[O+56]), "+f"(d[O+57]), "+f"(d[O+58]), "+f"(d[O+59]), "+f"(d[O+60]), "+f"(d[O+61]), "+f"(d[O+62]), "+f"(d[O+63])
   : "l"(da), "l"(db), "n"(TB & 1), "n"(TB >> 1));
  else if constexpr (ACC == 0) asm volatile("wgmma.mma_async.sync.aligned.m64n128k16.f32.bf16.bf16 {%0,%1,%2,%3,%4,%5,%6,%7,%8,%9,%10,%11,%12,%13,%14,%15,%16,%17,%18,%19,%20,%21,%22,%23,%24,%25,%26,%27,%28,%29,%30,%31,%32,%33,%34,%35,%36,%37,%38,%39,%40,%41,%42,%43,%44,%45,%46,%47,%48,%49,%50,%51,%52,%53,%54,%55,%56,%57,%58,%59,%60,%61,%62,%63}, %64, %65, 0, 1, 1, %67, %66;"
   : "=f"(d[O+0]), "=f"(d[O+1]), "=f"(d[O+2]), "=f"(d[O+3]), "=f"(d[O+4]), "=f"(d[O+5]), "=f"(d[O+6]), "=f"(d[O+7]), "=f"(d[O+8]), "=f"(d[O+9]), "=f"(d[O+10]), "=f"(d[O+11]), "=f"(d[O+12]), "=f"(d[O+13]), "=f"(d[O+14]), "=f"(d[O+15]), "=f"(d[O+16]), "=f"(d[O+17]), "=f"(d[O+18]), "=f"(d[O+19]), "=f"(d[O+20]), "=f"(d[O+21]), "=f"(d[O+22]), "=f"(d[O+23]), "=f"(d[O+24]), "=f"(d[O+25]), "=f"(d[O+26]), "=f"(d[O+27]), "=f"(d[O+28]), "=f"(d[O+29]), "=f"(d[O+30]), "=f"(d[O+31]), "=f"(d[O+32]), "=f"(d[O+33]), "=f"(d[O+34]), "=f"(d[O+35]), "=f"(d[O+36]), "=f"(d[O+37]), "=f"(d[O+38]), "=f"(d[O+39]), "=f"(d[O+40]), "=f"(d[O+41]), "=f"(d[O+42]), "=f"(d[O+43]), "=f"(d[O+44]), "=f"(d[O+45]), "=f"(d[O+46]), "=f"(d[O+47]), "=f"(d[O+48]), "=f"(d[O+49]), "=f"(d[O+50]), "=f"(d[O+51]), "=f"(d[O+52]), "=f"(d[O+53]), "=f"(d[O+54]), "=f"(d[O+55]), "=f"(d[O+56]), "=f"(d[O+57]), "=f"(d[O+58]), "=f"(d[O+59]), "=f"(d[O+60]), "=f"(d[O+61]), "=f"(d[O+62]), "=f"(d[O+63])
   : "l"(da), "l"(db), "n"(TB & 1), "n"(TB >> 1));
  else asm volatile("{\n.reg .pred p;\nsetp.ne.b32 p, %68, 0;\nwgmma.mma_async.sync.aligned.m64n128k16.f32.bf16.bf16 {%0,%1,%2,%3,%4,%5,%6,%7,%8,%9,%10,%11,%12,%13,%14,%15,%16,%17,%18,%19,%20,%21,%22,%23,%24,%25,%26,%27,%28,%29,%30,%31,%32,%33,%34,%35,%36,%37,%38,%39,%40,%41,%42,%43,%44,%45,%46,%47,%48,%49,%50,%51,%52,%53,%54,%55,%56,%57,%58,%59,%60,%61,%62,%63}, %64, %65, p, 1, 1, %67, %66;\n}"
   : "+f"(d[O+0]), "+f"(d[O+1]), "+f"(d[O+2]), "+f"(d[O+3]), "+f"(d[O+4]), "+f"(d[O+5]), "+f"(d[O+6]), "+f"(d[O+7]), "+f"(d[O+8]), "+f"(d[O+9]), "+f"(d[O+10]), "+f"(d[O+11]), "+f"(d[O+12]), "+f"(d[O+13]), "+f"(d[O+14]), "+f"(d[O+15]), "+f"(d[O+16]), "+f"(d[O+17]), "+f"(d[O+18]), "+f"(d[O+19]), "+f"(d[O+20]), "+f"(d[O+21]), "+f"(d[O+22]), "+f"(d[O+23]), "+f"(d[O+24]), "+f"(d[O+25]), "+f"(d[O+26]), "+f"(d[O+27]), "+f"(d[O+28]), "+f"(d[O+29]), "+f"(d[O+30]), "+f"(d[O+31]), "+f"(d[O+32]), "+f"(d[O+33]), "+f"(d[O+34]), "+f"(d[O+35]), "+f"(d[O+36]), "+f"(d[O+37]), "+f"(d[O+38]), "+f"(d[O+39]), "+f"(d[O+40]), "+f"(d[O+41]), "+f"(d[O+42]), "+f"(d[O+43]), "+f"(d[O+44]), "+f"(d[O+45]), "+f"(d[O+46]), "+f"(d[O+47]), "+f"(d[O+48]), "+f"(d[O+49]), "+f"(d[O+50]), "+f"(d[O+51]), "+f"(d[O+52]), "+f"(d[O+53]), "+f"(d[O+54]), "+f"(d[O+55]), "+f"(d[O+56]), "+f"(d[O+57]), "+f"(d[O+58]), "+f"(d[O+59]), "+f"(d[O+60]), "+f"(d[O+61]), "+f"(d[O+62]), "+f"(d[O+63])
   : "l"(da), "l"(db), "n"(TB & 1), "n"(TB >> 1), "r"(sd));
}
template<int O,int TB,int ACC,int NN> __device__ __forceinline__ void mma_rs128(float (&d)[NN], uint32_t a0, uint32_t a1, uint32_t a2, uint32_t a3, uint64_t db, int sd = 0){
  if constexpr (ACC == 1) asm volatile("wgmma.mma_async.sync.aligned.m64n128k16.f32.bf16.bf16 {%0,%1,%2,%3,%4,%5,%6,%7,%8,%9,%10,%11,%12,%13,%14,%15,%16,%17,%18,%19,%20,%21,%22,%23,%24,%25,%26,%27,%28,%29,%30,%31,%32,%33,%34,%35,%36,%37,%38,%39,%40,%41,%42,%43,%44,%45,%46,%47,%48,%49,%50,%51,%52,%53,%54,%55,%56,%57,%58,%59,%60,%61,%62,%63}, {%64,%65,%66,%67}, %68, 1, 1, 1, %69;"
   : "+f"(d[O+0]), "+f"(d[O+1]), "+f"(d[O+2]), "+f"(d[O+3]), "+f"(d[O+4]), "+f"(d[O+5]), "+f"(d[O+6]), "+f"(d[O+7]), "+f"(d[O+8]), "+f"(d[O+9]), "+f"(d[O+10]), "+f"(d[O+11]), "+f"(d[O+12]), "+f"(d[O+13]), "+f"(d[O+14]), "+f"(d[O+15]), "+f"(d[O+16]), "+f"(d[O+17]), "+f"(d[O+18]), "+f"(d[O+19]), "+f"(d[O+20]), "+f"(d[O+21]), "+f"(d[O+22]), "+f"(d[O+23]), "+f"(d[O+24]), "+f"(d[O+25]), "+f"(d[O+26]), "+f"(d[O+27]), "+f"(d[O+28]), "+f"(d[O+29]), "+f"(d[O+30]), "+f"(d[O+31]), "+f"(d[O+32]), "+f"(d[O+33]), "+f"(d[O+34]), "+f"(d[O+35]), "+f"(d[O+36]), "+f"(d[O+37]), "+f"(d[O+38]), "+f"(d[O+39]), "+f"(d[O+40]), "+f"(d[O+41]), "+f"(d[O+42]), "+f"(d[O+43]), "+f"(d[O+44]), "+f"(d[O+45]), "+f"(d[O+46]), "+f"(d[O+47]), "+f"(d[O+48]), "+f"(d[O+49]), "+f"(d[O+50]), "+f"(d[O+51]), "+f"(d[O+52]), "+f"(d[O+53]), "+f"(d[O+54]), "+f"(d[O+55]), "+f"(d[O+56]), "+f"(d[O+57]), "+f"(d[O+58]), "+f"(d[O+59]), "+f"(d[O+60]), "+f"(d[O+61]), "+f"(d[O+62]), "+f"(d[O+63])
   : "r"(a0), "r"(a1), "r"(a2), "r"(a3), "l"(db), "n"(TB));
  else if constexpr (ACC == 0) asm volatile("wgmma.mma_async.sync.aligned.m64n128k16.f32.bf16.bf16 {%0,%1,%2,%3,%4,%5,%6,%7,%8,%9,%10,%11,%12,%13,%14,%15,%16,%17,%18,%19,%20,%21,%22,%23,%24,%25,%26,%27,%28,%29,%30,%31,%32,%33,%34,%35,%36,%37,%38,%39,%40,%41,%42,%43,%44,%45,%46,%47,%48,%49,%50,%51,%52,%53,%54,%55,%56,%57,%58,%59,%60,%61,%62,%63}, {%64,%65,%66,%67}, %68, 0, 1, 1, %69;"
   : "=f"(d[O+0]), "=f"(d[O+1]), "=f"(d[O+2]), "=f"(d[O+3]), "=f"(d[O+4]), "=f"(d[O+5]), "=f"(d[O+6]), "=f"(d[O+7]), "=f"(d[O+8]), "=f"(d[O+9]), "=f"(d[O+10]), "=f"(d[O+11]), "=f"(d[O+12]), "=f"(d[O+13]), "=f"(d[O+14]), "=f"(d[O+15]), "=f"(d[O+16]), "=f"(d[O+17]), "=f"(d[O+18]), "=f"(d[O+19]), "=f"(d[O+20]), "=f"(d[O+21]), "=f"(d[O+22]), "=f"(d[O+23]), "=f"(d[O+24]), "=f"(d[O+25]), "=f"(d[O+26]), "=f"(d[O+27]), "=f"(d[O+28]), "=f"(d[O+29]), "=f"(d[O+30]), "=f"(d[O+31]), "=f"(d[O+32]), "=f"(d[O+33]), "=f"(d[O+34]), "=f"(d[O+35]), "=f"(d[O+36]), "=f"(d[O+37]), "=f"(d[O+38]), "=f"(d[O+39]), "=f"(d[O+40]), "=f"(d[O+41]), "=f"(d[O+42]), "=f"(d[O+43]), "=f"(d[O+44]), "=f"(d[O+45]), "=f"(d[O+46]), "=f"(d[O+47]), "=f"(d[O+48]), "=f"(d[O+49]), "=f"(d[O+50]), "=f"(d[O+51]), "=f"(d[O+52]), "=f"(d[O+53]), "=f"(d[O+54]), "=f"(d[O+55]), "=f"(d[O+56]), "=f"(d[O+57]), "=f"(d[O+58]), "=f"(d[O+59]), "=f"(d[O+60]), "=f"(d[O+61]), "=f"(d[O+62]), "=f"(d[O+63])
   : "r"(a0), "r"(a1), "r"(a2), "r"(a3), "l"(db), "n"(TB));
  else asm volatile("{\n.reg .pred p;\nsetp.ne.b32 p, %70, 0;\nwgmma.mma_async.sync.aligned.m64n128k16.f32.bf16.bf16 {%0,%1,%2,%3,%4,%5,%6,%7,%8,%9,%10,%11,%12,%13,%14,%15,%16,%17,%18,%19,%20,%21,%22,%23,%24,%25,%26,%27,%28,%29,%30,%31,%32,%33,%34,%35,%36,%37,%38,%39,%40,%41,%42,%43,%44,%45,%46,%47,%48,%49,%50,%51,%52,%53,%54,%55,%56,%57,%58,%59,%60,%61,%62,%63}, {%64,%65,%66,%67}, %68, p, 1, 1, %69;\n}"
   : "+f"(d[O+0]), "+f"(d[O+1]), "+f"(d[O+2]), "+f"(d[O+3]), "+f"(d[O+4]), "+f"(d[O+5]), "+f"(d[O+6]), "+f"(d[O+7]), "+f"(d[O+8]), "+f"(d[O+9]), "+f"(d[O+10]), "+f"(d[O+11]), "+f"(d[O+12]), "+f"(d[O+13]), "+f"(d[O+14]), "+f"(d[O+15]), "+f"(d[O+16]), "+f"(d[O+17]), "+f"(d[O+18]), "+f"(d[O+19]), "+f"(d[O+20]), "+f"(d[O+21]), "+f"(d[O+22]), "+f"(d[O+23]), "+f"(d[O+24]), "+f"(d[O+25]), "+f"(d[O+26]), "+f"(d[O+27]), "+f"(d[O+28]), "+f"(d[O+29]), "+f"(d[O+30]), "+f"(d[O+31]), "+f"(d[O+32]), "+f"(d[O+33]), "+f"(d[O+34]), "+f"(d[O+35]), "+f"(d[O+36]), "+f"(d[O+37]), "+f"(d[O+38]), "+f"(d[O+39]), "+f"(d[O+40]), "+f"(d[O+41]), "+f"(d[O+42]), "+f"(d[O+43]), "+f"(d[O+44]), "+f"(d[O+45]), "+f"(d[O+46]), "+f"(d[O+47]), "+f"(d[O+48]), "+f"(d[O+49]), "+f"(d[O+50]), "+f"(d[O+51]), "+f"(d[O+52]), "+f"(d[O+53]), "+f"(d[O+54]), "+f"(d[O+55]), "+f"(d[O+56]), "+f"(d[O+57]), "+f"(d[O+58]), "+f"(d[O+59]), "+f"(d[O+60]), "+f"(d[O+61]), "+f"(d[O+62]), "+f"(d[O+63])
   : "r"(a0), "r"(a1), "r"(a2), "r"(a3), "l"(db), "n"(TB), "r"(sd));
}

#define NEARLY 0
#define XAHEAD 3
#define HM 2
#define WBATCH 1
#define SPACE 0
#define WPF 1
#define WAFTER 7
#define WPACE 0
#define GATE_AT 4
#define TPACE 40
#define PFMODE 0
#define MAPMODE 0
template <int V> struct IC { static constexpr int value = V; };
struct Maps { CUtensorMap x, ft, g64, u64, e, wr, wi, xs, ts, t, g32, u32, d224; };

constexpr int NCTA = 130;
constexpr int U = 16384;
constexpr int TB = 36864;
constexpr int OFF_RING = 8 * U, OFF_Z = 9 * U, OFF_XB = 12 * U, OFF_T = 13 * U, OFF_D = OFF_T;
constexpr int OFF_BAR = 14 * U, OFF_SP = OFF_BAR + 512, OFF_G = OFF_SP + 1024 + 128;
constexpr int SMEM_BYTES = OFF_G + 512;
constexpr int B_FX = 0, B_FA = 8, B_FT = 12, B_Z = 16, B_W = 20, B_HX = 21, B_TL = 22, B_HP = 23, B_WR = 26, B_E0 = 30;
constexpr int B_EA = 31, B_ET = 35, B_PZ = 39, B_RDY = 41, B_FE = 42;
constexpr int B_T = 46, B_XS = 47, B_G = 49, NBAR = 50;
__host__ __device__ constexpr int rslot(int n) { return n & 3; }
__host__ __device__ constexpr int rpar(int n) { return (n >> 2) & 1; }

__global__ void __cluster_dims__(2, 1, 1) __launch_bounds__(512, 1)
fused_kernel(const __grid_constant__ Maps maps, const __nv_bfloat16* __restrict__ w_r,
             const __nv_bfloat16* __restrict__ w_i, const __nv_bfloat16* __restrict__ gate_w, __nv_bfloat16* __restrict__ out) {
  extern __shared__ __align__(1024) uint8_t smem[];
  const uint32_t sb = smem_u32(smem);
  const uint32_t bars = sb + OFF_BAR;
  const int tid = threadIdx.x, lane = tid & 31;
  const int warp = __shfl_sync(0xffffffffu, tid >> 5, 0);
  const bool helper = blockIdx.x >= 128;
  const int cl = (blockIdx.x >> 1) & 63, rank = blockIdx.x & 1;
  const int q4 = cl & 3, rb = cl >> 2;
  const int j = 2 * q4 + rank;
  const int f_full = 448 * q4 + (rank ? 256 : 0);
  const int f_half = 448 * q4 + (rank ? 224 : 192);
  const int kg = 2 * j + (rb >> 3), tn = rb & 7;

  if (tid == 64) { PROF_EV(0); PROF_CK(40); }
  if (warp < 8) {
    asm volatile("barrier.cluster.arrive.relaxed.aligned;" ::: "memory");
    asm volatile("setmaxnreg.inc.sync.aligned.u32 192;");
    if (!helper) {
      const int wg = warp >> 2, w = warp & 3, g = lane >> 2;
      const bool elect = (tid & 127) == 0;
      float cX[32], cA[64], cB[64], cC[64], ci[64], ct[64];
      const int zero = blockIdx.x >> 16;
      uint32_t h[56], yf[16];
      const uint32_t d0 = (sb & 0x3FFFF) >> 4;
      const uint32_t dK = d0 | (1u << 16), dN = d0 | (512u << 16);
      const uint32_t dX = dK + wg * 512;
      constexpr uint32_t RING = OFF_RING >> 4;
      auto waitA = [&](int n) { mbar_wait(bars + 8 * (B_FA + rslot(n)), rpar(n)); };
      auto freeA = [&](int n) { mbar_arrive_if(elect, bars + 8 * (B_EA + rslot(n))); };
      auto nop = [] {};

      asm volatile("bar.sync 0, 384;" ::: "memory");
#pragma unroll 1
      for (int i = 0; i < 4; i++) {
        const uint64_t dx = d128(dX + i * 2048), df = d128(dK + (OFF_XB >> 4) + (i & 1) * 1024);
        mbar_wait(bars + 8 * (B_FX + 2 * i), 0);
        wg_fence();
        mma_ss64<0, 0, 2>(cX, df, dx, i);
        mma_ss64<0, 0, 1>(cX, df + 2, dx + 2);
        wg_commit(); wg_wait<1>();
        mbar_arrive_if(elect && i, bars + 8 * (B_EA + rslot(i - 1)));
        mma_ss64<0, 0, 1>(cX, df + 4, dx + 4);
        mma_ss64<0, 0, 1>(cX, df + 6, dx + 6);
        if (i == 0 && tid == 0) PROF_EV(1);
        mbar_wait(bars + 8 * (B_FX + 2 * i + 1), 0);
        wg_fence();
#pragma unroll
        for (int k = 0; k < 4; k++) mma_ss64<0, 0, 1>(cX, df + (512 + k * 2), dx + (1024 + k * 2));
        wg_commit();
        waitA(i);
        wg_fence();
        const uint64_t da = d128(dX + i * 1024), db = d128(dN + RING + i * 1024);
        mma_ss128<0, 1, 2>(cA, da, db, i);
        wg_commit(); wg_wait<1>();
        mbar_arrive_if(elect, bars + 8 * (B_FE + i));
#pragma unroll
        for (int k = 1; k < 4; k++) mma_ss128<0, 1, 1>(cA, da + k * 2, db + k * 128);
        wg_commit();
      }
      fence_regs<0, 32>(cX);
#pragma unroll
      for (int e = 0; e < 16; e++) yf[e] = pack_pin(cX[2 * e], cX[2 * e + 1]);
      if (tid == 0) PROF_EV(2);
      {
        waitA(4); mbar_wait(bars + 8 * B_E0, 0);
        const uint64_t de = d128(dN + (wg ? RING : OFF_XB >> 4));
        wg_fence();
        mma_rs128<0, 1, 0>(cB, yf[0], yf[1], yf[2], yf[3], de);
        wg_commit();
        wg_wait<1>();
        freeA(3);
#pragma unroll
        for (int k = 1; k < 4; k++) mma_rs128<0, 1, 1>(cB, yf[4 * k], yf[4 * k + 1], yf[4 * k + 2], yf[4 * k + 3], de + k * 128);
        wg_commit();
      }
      bool rel = false;
      auto acquire = [&](int n) {
        rel = elect;
        if (!mbar_try(bars + 8 * (B_FA + rslot(n)), rpar(n))) { wg_wait<0>(); freeA(n - 1); rel = false; waitA(n); }
      };
      auto freeP = [&](int n) { mbar_arrive_if(rel, bars + 8 * (B_EA + rslot(n - 1))); };
      auto ffn_step = [&](auto first, auto split, float (&acc)[64], int n, int kb, auto done, auto work) {
        constexpr int SPLIT = decltype(split)::value;
        acquire(n);
        wg_fence();
        const uint64_t dx = d128(dX + kb * 1024), db = d128(dN + RING + rslot(n) * 1024);
        mma_ss128<0, 1, decltype(first)::value>(acc, dx, db, zero);
#pragma unroll
        for (int k = 1; k < SPLIT; k++) mma_ss128<0, 1, 1>(acc, dx + k * 2, db + k * 128);
        wg_commit();
        work();
        wg_wait<1>();
        freeP(n);
        done();
        if (SPLIT < 4) {
          wg_fence();
#pragma unroll
          for (int k = SPLIT; k < 4; k++) mma_ss128<0, 1, 1>(acc, dx + k * 2, db + k * 128);
          wg_commit();
        }
      };
      {
        const int s0 = 2 * rb + wg, kr = 2 * ((s0 & 1) | ((s0 & 4) >> 1));
        const int m = lane >> 3, r = lane & 7;
        const uint32_t a0 = sb + OFF_XB + wg * 8192 + (((w >> 1) * 8 + (m >> 1)) * 2 + (w & 1)) * 256 + (m & 1) * 128 + ((r ^ (kr + (m & 1))) << 4);
        ffn_step(IC<1>(), IC<4>(), cA, 5, 4, [&] { fence_regs<0, 64>(cB); }, nop);
        asm volatile("bar.sync 5, 256;" ::: "memory");
#pragma unroll
        for (int i = 0; i < 4; i++)
          stsm4t(a0 + i * 1024, pack_bf16(cB[8 * i] - cB[34 + 8 * i], cB[8 * i + 1] - cB[35 + 8 * i]),
                 pack_bf16(cB[32 + 8 * i] + cB[8 * i + 2], cB[33 + 8 * i] + cB[8 * i + 3]),
                 pack_bf16(cB[8 * i + 4] - cB[38 + 8 * i], cB[8 * i + 5] - cB[39 + 8 * i]),
                 pack_bf16(cB[36 + 8 * i] + cB[8 * i + 6], cB[37 + 8 * i] + cB[8 * i + 7]));
        if (j == 0 && w == 0) {
          const uint32_t a1 = r ? sb + OFF_SP + 1024 : sb + OFF_SP + wg * 512 + (m & 1) * 256 + (m >> 1) * 128;
#pragma unroll
          for (int n = 0; n < 8; n++)
            asm volatile("stmatrix.sync.aligned.m8n8.x4.shared.b16 [%0], {%1,%2,%3,%4};" ::"r"(a1 + ((n ^ (kr + (m >> 1))) << 4)),
                         "r"(pack_bf16(cB[4 * n], cB[4 * n + 1])), "r"(pack_bf16(cB[4 * n + 2], cB[4 * n + 3])),
                         "r"(pack_bf16(cB[32 + 4 * n], cB[33 + 4 * n])), "r"(pack_bf16(cB[34 + 4 * n], cB[35 + 4 * n])) : "memory");
        }
        ffn_step(IC<1>(), IC<2>(), cA, 6, 5, nop, [&] {
          asm volatile("fence.proxy.async.shared::cta;" ::: "memory");
          __syncwarp();
          mbar_arrive_if(lane == 0, bars + 8 * (B_XS + wg));
          if (tid == 0) PROF_EV(3);
        });
      }
#pragma unroll 1
      for (int kb = 6; kb < 8; kb++) ffn_step(IC<1>(), IC<1>(), cA, 1 + kb, kb, nop, nop);
      ffn_step(IC<2>(), IC<1>(), cB, 9, 0, [&] { fence_regs<0, 64>(cA); }, nop);
#pragma unroll 1
      for (int kb = 1; kb < 6; kb++) ffn_step(IC<1>(), IC<1>(), cB, 9 + kb, kb, nop, nop);
      mbar_wait(bars + 8 * B_G, 0);
      const uint32_t gb0 = *(const uint32_t*)(smem + OFF_G + (wg * 64 + w * 16 + g) * 4), gb1 = *(const uint32_t*)(smem + OFF_G + (wg * 64 + w * 16 + g + 8) * 4);
      const uint32_t tag = gb0 & 1;
      const float g0 = __uint_as_float(gb0 & ~1u), g1 = __uint_as_float(gb1 & ~1u);
      const float o0 = 1.0f - g0, o1 = 1.0f - g1;
      auto glu = [&](auto& acc, int half, int ho, int i0, int i1) {
#pragma unroll
        for (int i = i0; i < i1; i++) {
          const float o = (i & 1) ? o1 : o0;
          h[ho + i] = pack_pin(fmaxf(acc[2 * i], 0.f) * acc[half + 2 * i] * o, fmaxf(acc[2 * i + 1], 0.f) * acc[half + 1 + 2 * i] * o);
        }
      };
      ffn_step(IC<1>(), IC<1>(), cB, 15, 6, nop, [&] { glu(cA, 32, 0, 0, 8); });
      ffn_step(IC<1>(), IC<1>(), cB, 16, 7, nop, [&] { glu(cA, 32, 0, 8, 16); });
      ffn_step(IC<0>(), IC<1>(), cC, 17, 0, [&] { fence_regs<0, 64>(cB); }, nop);
      if (tid == 0) PROF_EV(4);
      ffn_step(IC<1>(), IC<1>(), cC, 18, 1, nop, [&] { glu(cB, 32, 16, 0, 8); });
      ffn_step(IC<1>(), IC<1>(), cC, 19, 2, nop, [&] { glu(cB, 32, 16, 8, 16); });
#pragma unroll 1
      for (int kb = 3; kb < 8; kb++) ffn_step(IC<1>(), IC<1>(), cC, 17 + kb, kb, nop, nop);
      if (tid == 0) PROF_EV(5);
      auto m_step = [&](auto first, int i, auto done, auto work) {
        acquire(25 + i);
        wg_fence();
        const uint64_t dx = d128(dX + i * 2048), dm = d64(dN + RING + rslot(25 + i) * 1024);
        mma_ss64<0, 1, decltype(first)::value>(ct, dx, dm);
        mma_ss64<0, 1, 1>(ct, dx + 2, dm + 64);
        wg_commit();
        work();
        wg_wait<1>();
        freeP(25 + i);
        done();
        wg_fence();
#pragma unroll
        for (int k = 2; k < 8; k++) mma_ss64<0, 1, 1>(ct, dx + ((k >> 2) * 1024 + (k & 3) * 2), dm + k * 64);
        wg_commit();
      };
      auto freeT = [&](int t) { mbar_arrive_if(elect, bars + 8 * (B_ET + t)); };
      m_step(IC<0>(), 0, [&] { fence_regs<0, 64>(cC); }, nop);
      m_step(IC<1>(), 1, [&] { freeT(0); }, [&] { glu(cC, 32, 32, 0, 5); });
      m_step(IC<1>(), 2, [&] { freeT(1); }, [&] { glu(cC, 32, 32, 5, 11); });
      m_step(IC<1>(), 3, [&] { freeT(2); }, [&] { glu(cC, 32, 32, 11, 16); });
      waitA(29 + wg);
      if (tid == 0) PROF_EV(6);
      mbar_wait(bars + 8 * (j == 0 ? B_T : B_TL), 0);
      if (tid == 0) PROF_EV(7);
      wg_fence();
      {
        const uint64_t dt = d128(dN + (OFF_T >> 4) + wg * 512), de = d128(dK + RING + (1 + wg) * 1024);
        mma_ss64<0, 1, 0>(ci, de, dt);
        mma_ss64<32, 1, 0>(ci, de + 512, dt);
#pragma unroll
        for (int k = 1; k < 4; k++) {
          mma_ss64<0, 1, 1>(ci, de + k * 2, dt + k * 128);
          mma_ss64<32, 1, 1>(ci, de + (512 + k * 2), dt + k * 128);
        }
        wg_commit();
        wg_wait<1>();
        freeT(3);
        fence_regs<0, 32>(ct);
        glu(ct, 16, 48, 0, 8);
      }

      auto head = [&](auto off, int t, auto first) {
        constexpr int O = decltype(off)::value;
        mbar_wait(bars + 8 * (B_FT + (t & 3)), t >> 2);
        const uint64_t db = d128(dN + (t & 3) * (TB >> 4) + rank * 256);
        wg_fence();
        mma_rs64<O, 1, decltype(first)::value>(ct, h[0], h[1], h[2], h[3], db, zero);
#pragma unroll
        for (int k = 1; k < 6; k++) mma_rs64<O, 1, 1>(ct, h[4 * k], h[4 * k + 1], h[4 * k + 2], h[4 * k + 3], db + k * 128);
        wg_commit();
        wg_wait<1>();
      };
      auto rest = [&](auto off, int t) {
        constexpr int O = decltype(off)::value;
        const uint64_t db = d128(dN + (t & 3) * (TB >> 4)), dw = db + rank * 256, dm = db + (rank ? 0 : 1536);
        wg_fence();
#pragma unroll
        for (int k = 6; k < 12; k++) mma_rs64<O, 1, 1>(ct, h[4 * k], h[4 * k + 1], h[4 * k + 2], h[4 * k + 3], dw + k * 128);
#pragma unroll
        for (int k = 0; k < 2; k++) mma_rs64<O, 1, 1>(ct, h[48 + 4 * k], h[49 + 4 * k], h[50 + 4 * k], h[51 + 4 * k], dm + k * 128);
#pragma unroll
        for (int k = 0; k < 4; k++) mma_rs64<O, 1, 1>(ct, yf[4 * k], yf[4 * k + 1], yf[4 * k + 2], yf[4 * k + 3], db + (14 + k) * 128);
        wg_commit();
      };
      const uint32_t peerZ = mapa(sb + OFF_Z + tid * 16, rank ^ 1), peerB = mapa(bars + 8 * B_Z, rank ^ 1);
      auto send = [&](auto off, int t) {
        constexpr int O = decltype(off)::value;
        fence_regs<O, 32>(ct);
        const bool grid = t >= 3 && t < 6;
        const int z = grid ? t - 3 : t == 6 ? 3 : t;
        if (grid) {
          mbar_wait(bars + 8 * (B_Z + z), 0);
#pragma unroll
          for (int i = 0; i < 4; i++) {
            const uint4 p = *(const uint4*)(smem + OFF_Z + z * U + i * 4096 + tid * 16);
            const uint32_t a[4] = {p.x, p.y, p.z, p.w};
#pragma unroll
            for (int e = 0; e < 4; e++) { ct[O + 8 * i + 2 * e] += bf_lo(a[e]); ct[O + 8 * i + 2 * e + 1] += bf_hi(a[e]); }
          }
        }
        uint32_t pk[16];
#pragma unroll
        for (int i = 0; i < 16; i++) pk[i] = pack_bf16(ct[O + 2 * i], ct[O + 2 * i + 1]);
        if (grid) {
          const int owner = rb * 8 + 2 * ((q4 + z + 1) & 3) + rank;
          uint4* dst = g_part + (size_t)(owner * 3 + z) * 1024 + tid;
#pragma unroll
          for (int i = 0; i < 4; i++) st_x4(dst + i * 256, (pk[4 * i] & ~1u) | tag, pk[4 * i + 1], pk[4 * i + 2], pk[4 * i + 3]);
          __syncwarp();
          hint_add_if(lane == 0, &g_cntP[32 * owner + z]);
        } else {
#pragma unroll
          for (int i = 0; i < 4; i++)
            asm volatile("st.async.weak.shared::cluster.mbarrier::complete_tx::bytes.v4.b32 [%0], {%1,%2,%3,%4}, [%5];" ::"r"(peerZ + z * U + i * 4096),
                         "r"(pk[4 * i]), "r"(pk[4 * i + 1]), "r"(pk[4 * i + 2]), "r"(pk[4 * i + 3]), "r"(peerB + 8 * z) : "memory");
        }
      };
      asm volatile("barrier.cluster.wait.aligned;" ::: "memory");
      head(IC<0>(), 0, IC<2>());
      if (elect) asm volatile("mbarrier.arrive.shared::cluster.b64 _, [%0];" ::"r"(mapa(bars + 8 * B_RDY, rank ^ 1)) : "memory");
      fence_regs<0, 64>(ci);
#pragma unroll
      for (int i = 0; i < 16; i++) {
        const float gg = ((i & 1) ? g1 : g0) * (2.0f / (2048.0f * 512.0f));
        if (i & 2) yf[i] = pack_pin((ci[2 * i] - ci[28 + 2 * i]) * gg, (ci[2 * i + 1] - ci[29 + 2 * i]) * gg);
        else yf[i] = pack_pin((ci[2 * i] + ci[36 + 2 * i]) * gg, (ci[2 * i + 1] + ci[37 + 2 * i]) * gg);
      }
      if (tid == 0) PROF_EV(8);
#pragma unroll 1
      for (int t = 0;; t += 2) {
        rest(IC<0>(), t);
        head(IC<32>(), t + 1, IC<2>());
        mbar_arrive_if(elect && t < 6, bars + 8 * (B_ET + t));
        if (t == 0) mbar_wait(bars + 8 * B_RDY, 0);
        send(IC<0>(), t);
        rest(IC<32>(), t + 1);
        if (t == 6) break;
        head(IC<0>(), t + 2, IC<2>());
        mbar_arrive_if(elect, bars + 8 * (B_ET + t + 1));
        send(IC<32>(), t + 1);
      }
      if (tid == 0) PROF_EV(9);
      {
        float sum[32];
        mbar_wait(bars + 8 * (B_Z + 3), 0);
#pragma unroll
        for (int i = 0; i < 4; i++) {
          const uint4 p = *(const uint4*)(smem + OFF_Z + 3 * U + i * 4096 + tid * 16);
          const uint32_t a[4] = {p.x, p.y, p.z, p.w};
#pragma unroll
          for (int e = 0; e < 4; e++) { sum[8 * i + 2 * e] = bf_lo(a[e]); sum[8 * i + 2 * e + 1] = bf_hi(a[e]); }
        }
#pragma unroll 1
        for (int z = 0; z < 3; z++) {
          mbar_wait(bars + 8 * (B_HP + z), 0);
          if (z == 2 && tid == 0) PROF_EV(24);
          uint4 pv[4];
#pragma unroll
          for (int i = 0; i < 4; i++) pv[i] = *(const uint4*)(smem + z * U + i * 4096 + tid * 16);
          const uint32_t t0 = (uint32_t)clock();
          while (__any_sync(0xffffffffu, ((pv[0].x ^ tag) | (pv[1].x ^ tag) | (pv[2].x ^ tag) | (pv[3].x ^ tag)) & 1)) {
#pragma unroll
            for (int i = 0; i < 4; i++) pv[i] = ld_x4(g_part + (size_t)((rb * 8 + j) * 3 + z) * 1024 + tid + i * 256);
            spin_guard(t0);
          }
#pragma unroll
          for (int i = 0; i < 4; i++) {
            const uint32_t a[4] = {pv[i].x & ~1u, pv[i].y, pv[i].z, pv[i].w};
#pragma unroll
            for (int e = 0; e < 4; e++) { sum[8 * i + 2 * e] += bf_lo(a[e]); sum[8 * i + 2 * e + 1] += bf_hi(a[e]); }
          }
        }
        if (tid == 0) PROF_EV(14);
        wg_wait<0>();
        fence_regs<32, 32>(ct);
#pragma unroll
        for (int i = 0; i < 32; i++) sum[i] += ct[32 + i];
        const uint32_t stg = sb + OFF_T + warp * 2048;
        const int mr = (lane & 7) + ((lane >> 3) & 1) * 8, mc = lane >> 4;
#pragma unroll
        for (int i = 0; i < 4; i++) {
          const uint32_t a = stg + mr * 128 + (((2 * i + mc) ^ (mr & 7)) << 4);
          asm volatile("stmatrix.sync.aligned.m8n8.x4.shared.b16 [%0], {%1,%2,%3,%4};" ::"r"(a), "r"(pack_bf16(sum[8 * i], sum[8 * i + 1])),
                       "r"(pack_bf16(sum[8 * i + 2], sum[8 * i + 3])), "r"(pack_bf16(sum[8 * i + 4], sum[8 * i + 5])),
                       "r"(pack_bf16(sum[8 * i + 6], sum[8 * i + 7])) : "memory");
        }
        __syncwarp();
#pragma unroll
        for (int i = 0; i < 4; i++) {
          const int r = 4 * i + (lane >> 3), c = lane & 7;
          const uint4 v = *(const uint4*)(smem + OFF_T + warp * 2048 + r * 128 + ((c ^ (r & 7)) << 4));
          *(uint4*)(out + (size_t)(2 * rb + wg + 32 * (16 * w + r)) * 512 + 64 * j + 8 * c) = v;
        }
      }
      if (tid == 0) { PROF_EV(15); PROF_CK(41); }
    }
  } else if (warp < 12) {
    asm volatile("setmaxnreg.dec.sync.aligned.u32 104;");
    asm volatile("barrier.cluster.arrive.relaxed.aligned;" ::: "memory");
    const int t = tid - 256, w = warp - 8;
    const uint32_t ep = ld_x1(&g_epoch[blockIdx.x * 8]);
    const uint32_t tag = (ep + 1) & 1;
    auto w_issue = [&](const CUtensorMap* m) {
          if (lane == 0) { mbar_expect_tx(bars + 8 * (B_WR + w), 3072); tma4d(sb + OFF_T + w * 3072, m, bars + 8 * (B_WR + w), 16 * kg, 0, 2 * w, tn); }
          __syncwarp();
    };
    auto gate_rows = [&] {
      const int r = 16 * j + 4 * w + (lane >> 3);
      const uint4* pg = (const uint4*)gate_w + (lane & 7);
      {
        float a = 0.f;
        asm volatile("bar.sync 4, 256;" ::: "memory");
#pragma unroll 1
        for (int hf = 0; hf < 2; hf++) {
          uint4 v[4], u[4];
#pragma unroll
          for (int kb = 0; kb < 4; kb++) v[kb] = __ldg(pg + (4 * hf + kb) * 8);
          if (hf == 0) {
            mbar_wait(bars + 8 * (B_FX + WPF), 0);
            const int o = (8 * tn + 2 * w + 64 * lane) * 257 + 16 * kg + 8;
#pragma unroll
            for (int i = 0; i < 4; i++) asm volatile("prefetch.global.L2 [%0];" ::"l"(((i & 2) ? w_i : w_r) + o + (i & 1) * 257));
          }
          mbar_wait(bars + 8 * (B_FE + 1 + 2 * hf), 0);
          if (hf) w_issue(&maps.wr);
#pragma unroll
          for (int kb = 0; kb < 4; kb++) u[kb] = *(const uint4*)(smem + (4 * hf + kb) * U + r * 128 + (((lane ^ r) & 7) << 4));
#pragma unroll
          for (int kb = 0; kb < 4; kb++) {
            a = fmaf(bf_lo(u[kb].x), bf_lo(v[kb].x), a); a = fmaf(bf_hi(u[kb].x), bf_hi(v[kb].x), a);
            a = fmaf(bf_lo(u[kb].y), bf_lo(v[kb].y), a); a = fmaf(bf_hi(u[kb].y), bf_hi(v[kb].y), a);
            a = fmaf(bf_lo(u[kb].z), bf_lo(v[kb].z), a); a = fmaf(bf_hi(u[kb].z), bf_hi(v[kb].z), a);
            a = fmaf(bf_lo(u[kb].w), bf_lo(v[kb].w), a); a = fmaf(bf_hi(u[kb].w), bf_hi(v[kb].w), a);
          }
        }
#pragma unroll
        for (int o = 4; o; o >>= 1) a += __shfl_xor_sync(0xffffffffu, a, o);
        if ((lane & 7) == 0)
          asm volatile("st.relaxed.gpu.global.f32 [%0], %1;" ::"l"(g_gate + rb * 128 + r), "f"(tagf(__fdividef(1.0f, 1.0f + __expf(-a)), tag)) : "memory");
        if (t == 0) PROF_EV(18);
      }
    };
    {
      const int g = lane >> 2, q = lane & 3;
      uint32_t wf[32];
      if (!helper) {
        gate_rows();
        const uint32_t wa = sb + OFF_T + w * (3072 + 4) + q * 48 + g * 2;
#pragma unroll 1
        for (int ri = 0; ri < 2; ri++) {
          mbar_wait(bars + 8 * (B_WR + w), ri);
#pragma unroll
          for (int n2 = 0; n2 < 2; n2++) {
            uint32_t v[16];
#pragma unroll
            for (int i = 0; i < 16; i++)
              asm volatile("ld.shared.u16 %0, [%1];" : "=r"(v[i]) : "r"(wa + (4 * n2 + ((i >> 1) & 3)) * 192 + (i & 1) * (1536 + 2) + (i >> 3) * 16) : "memory");
#pragma unroll
            for (int i = 0; i < 16; i++) {
              uint32_t& d = wf[(i >> 3) * 16 + 8 * n2 + (i & 7)];
              d = __byte_perm(d, v[i], 0x5432);
              asm volatile("" : "+r"(d)::"memory");
            }
          }
          __syncwarp();
          if (ri == 0) w_issue(&maps.wi);
        }
        asm volatile("bar.sync 1, 128;" ::: "memory");
        if (t == 0) PROF_EV(11);
      } else {
        asm volatile("bar.sync 4, 256;" ::: "memory");
        hint_wait(&g_cntW[0], (ep + 1) * 128u);
        const uint32_t t0 = (uint32_t)clock();
#pragma unroll 1
        for (;;) {
          uint32_t bad = 0;
#pragma unroll
          for (int i = 0; i < 32; i++) {
            const float2 v = ld_x2((const float2*)g_Wh + (i >> 4) * 2048 + 16 * w + g + 8 * (i & 1) + 64 * q + ((i >> 1) & 7) * 256);
            wf[i] = __float_as_uint(v.x); bad |= __float_as_uint(v.y) ^ tag;
          }
          if (!__any_sync(0xffffffffu, bad & 1)) break;
          spin_guard(t0);
        }
        if (t == 0) PROF_EV(11);
      }
      if (t == 0) { mbar_expect_tx(bars + 8 * B_W, 8192); bulk_load(sb + OFF_D, g_DT.v, 8192, bars + 8 * B_W); }
      if (!helper) {
        const uint32_t t0 = (uint32_t)clock();
        uint32_t v;
        do { v = ld_x1(g_gate + rb * 128 + t); spin_guard(t0); } while (__any_sync(0xffffffffu, (v ^ tag) & 1));
        *(uint32_t*)(smem + OFF_G + t * 4) = v;
        __syncwarp();
        mbar_arrive_if(lane == 0, bars + 8 * B_G);
      }
      mbar_wait(bars + 8 * B_W, 0);
      mbar_wait(bars + 8 * B_HX, 0);
      if (t == 0) PROF_EV(12);
      const uint32_t dd = (sb & 0x3FFFF) >> 4;
      const uint64_t dF = d128((dd + (OFF_D >> 4)) | (512u << 16)), dI = d128((dd + (OFF_D >> 4)) | (1u << 16)), dA = d128((dd + (OFF_XB >> 4)) | (512u << 16));
      float az[32];
      const int zero = blockIdx.x >> 16;
      uint32_t pf[32];
#pragma unroll
      for (int mt = 0; mt < 2; mt++) {
        wg_fence();
        if (mt == 0) mma_ss64<0, 3, 0>(az, dA, dF);
        else mma_ss64<0, 3, 2>(az, dA + 512, dF, zero);
#pragma unroll
        for (int k = 1; k < 4; k++) mma_ss64<0, 3, 1>(az, dA + (mt * 512 + k * 128), dF + k * 128);
        wg_commit();
        wg_wait<0>();
        fence_regs<0, 32>(az);
#pragma unroll
        for (int i = 0; i < 16; i++) {
          const float wr = bf_lo(wf[16 * mt + i]), wi = bf_hi(wf[16 * mt + i]);
          pf[16 * mt + i] = pack_pin(fmaf(az[2 * i], wr, -az[2 * i + 1] * wi), fmaf(az[2 * i], wi, az[2 * i + 1] * wr));
        }
      }
      if (t == 0) PROF_EV(16);
#pragma unroll
      for (int mt = 0; mt < 2; mt++) {
        wg_fence();
        mma_rs64<0, 0, 2>(az, pf[16 * mt], pf[16 * mt + 1], pf[16 * mt + 2], pf[16 * mt + 3], dI, mt ? (int)helper : zero);
#pragma unroll
        for (int k = 1; k < 4; k++) mma_rs64<0, 0, 1>(az, pf[16 * mt + 4 * k], pf[16 * mt + 4 * k + 1], pf[16 * mt + 4 * k + 2], pf[16 * mt + 4 * k + 3], dI + k * 2);
        wg_commit();
        wg_wait<0>();
        fence_regs<0, 32>(az);
        if (!helper) {
          const int m = lane >> 3, r = lane & 7;
          const int sl = 2 * (m >> 1) + ((r >> 1) & 1) + 4 * (r >> 2);
          const uint32_t a0 = sb + OFF_XB + (2 * w + (m & 1)) * 2048 + sl * 64 + (((mt * 2 + (r & 1)) ^ (sl >> 1)) << 4);
#pragma unroll
          for (int i = 0; i < 4; i++)
            stsm4t(a0 + i * 512, pack_bf16(az[8 * i], az[8 * i + 1]), pack_bf16(az[8 * i + 2], az[8 * i + 3]), pack_bf16(az[8 * i + 4], az[8 * i + 5]),
                   pack_bf16(az[8 * i + 6], az[8 * i + 7]));
        }
      }
      if (helper) {
#pragma unroll
        for (int i = 0; i < 16; i++) {
          const int n = i >> 1, s0 = 8 * (n >> 1) + 2 * (n & 1) + (q & 1) + 4 * (q >> 1);
          if ((n & 1) == (int)(blockIdx.x & 1)) st_u2(g_Ts + s0 * 64 + 16 * w + g + 8 * (i & 1), pack_bf16(az[2 * i], az[2 * i + 1]), tag);
        }
        __syncwarp();
        hint_add_if(lane == 0, &g_cntH[0]);
        if (t == 0) { g_epoch[blockIdx.x * 8] = ep + 1; PROF_EV(13); }
      } else {
        asm volatile("fence.proxy.async.shared::cta;" ::: "memory");
        __syncwarp();
        if (lane == 0) {
          if (t == 0) PROF_EV(17);
          if (SPACE) __nanosleep(SPACE * w);
          asm volatile("cp.async.bulk.tensor.3d.global.shared::cta.bulk_group [%0, {%2, %3, %4}], [%1];" ::"l"(&maps.ts), "r"(sb + OFF_XB + w * 4096),
                       "r"(32 * kg), "r"(0), "r"(8 * tn + 2 * w) : "memory");
          bulk_done_signal(&g_cntT[32 * j]);
          if (t == 96) PROF_EV(13);
        }
        __syncwarp();
        if (j == 0) {
          hint_wait(&g_cntH[0], (ep + 1) * 8u);
          const uint32_t t0 = (uint32_t)clock();
          float2 v;
          do { v = ld_x2((const float2*)g_Ts + 2 * rb * 64 + t); spin_guard(t0); } while (__any_sync(0xffffffffu, (__float_as_uint(v.y) ^ tag) & 1));
          mbar_wait(bars + 8 * B_TL, 0);
          const uint32_t u = __float_as_uint(v.x);
          *(uint16_t*)(smem + OFF_T + t * 128 + ((t & 7) << 4)) = (uint16_t)u;
          *(uint16_t*)(smem + OFF_T + t * 128 + (((t & 7) ^ 1) << 4)) = (uint16_t)(u >> 16);
          asm volatile("fence.proxy.async.shared::cta;" ::: "memory");
          __syncwarp();
          mbar_arrive_if(lane == 0, bars + 8 * B_T);
        }
      }
    }
  } else {
    asm volatile("setmaxnreg.dec.sync.aligned.u32 24;");
    auto xf_load = [&](int q) {
      const uint32_t fb = bars + 8 * (B_FX + q);
      mbar_expect_tx(fb, U + 8192);
      tma3d(sb + q * U, &maps.x, fb, 64 * q, 0, 2 * rb);
      if (q >= 4) mbar_wait(bars + 8 * (B_FE + ((q - 4) >> 1)), 0);
      tma2d(sb + OFF_XB + (q & 3) * 8192, &maps.ft, fb, 64 * q, 64 * j);
    };
    if (lane == 0) {
      if (warp == 14) {
#pragma unroll
        for (int i = 0; i < B_FT; i++) mbar_init(bars + 8 * i, 1);
        asm volatile("fence.proxy.async.shared::cta;" ::: "memory");
        if (!helper) {
#pragma unroll 1
          for (int n = 0; n < 2; n++) {
            const uint32_t fb = bars + 8 * (B_FA + n);
            xf_load(2 * n); xf_load(2 * n + 1);
            mbar_expect_tx(fb, U);
            tma2d(sb + OFF_RING + n * U, &maps.g64, fb, f_full, 64 * n);
            tma2d(sb + OFF_RING + n * U + 8192, &maps.u64, fb, f_full, 64 * n);
          }
        }
      } else if (warp == 15) {
#pragma unroll
        for (int i = B_FT; i < NBAR; i++) mbar_init(bars + 8 * i, i < B_EA ? 1 : i < B_T ? 2 : 4);
#pragma unroll
        for (int i = 0; i < 4; i++) mbar_expect_tx(bars + 8 * (B_Z + i), U);
        asm volatile("fence.mbarrier_init.release.cluster;" ::: "memory");
        asm volatile("fence.proxy.async.shared::cta;" ::: "memory");
      } else if (warp == 13) {
#pragma unroll
        for (int i = 1; i < 4; i++) asm volatile("prefetch.tensormap [%0];" ::"l"((const char*)&maps + i * 128) : "memory");
      }
    }
    __syncwarp();
    asm volatile("bar.arrive 0, 384;" ::: "memory");
    asm volatile("bar.arrive 4, 256;" ::: "memory");
    __syncwarp();
    asm volatile("barrier.cluster.arrive.relaxed.aligned;" ::: "memory");
    asm volatile("bar.sync 3, 128;" ::: "memory");
    if (warp == 15 && !helper) {
        mbar_wait(bars + 8 * B_FE, 0);
        const uint32_t tag = (ld_x1(&g_epoch[blockIdx.x * 8]) + 1) & 1;
        const int c = lane >> 4, jj = 16 * blockIdx.x + (lane & 15), jm = (2048 - jj) & 2047;
        const unsigned short* pr = (const unsigned short*)w_r + 256 * c;
        const unsigned short* pi = (const unsigned short*)w_i + 256 * c;
        const float wr = 0.25f * (bf_lo(__ldg(pr + jj * 257)) + bf_lo(__ldg(pr + jm * 257)));
        const float wi = 0.25f * (bf_lo(__ldg(pi + jj * 257)) - bf_lo(__ldg(pi + jm * 257)));
        st_u2(g_Wh + c * 2048 + jj, c ? pack_bf16(-wi, wr) : pack_bf16(wr, wi), tag);
        __syncwarp();
        hint_add_if(lane == 0, &g_cntW[0]);
      }
    if (lane == 0 && (!helper || warp == 15)) {
      if (warp < 14) {
        const int p = warp - 12;
#pragma unroll 1
        for (int n = 2; n < 31; n++) {
          const bool table = n == 4 || n >= 29;
          const int q = n < 4 ? n : n - 1;
          const CUtensorMap* m = table ? &maps.e : n >= 25 ? &maps.g32 + p : &maps.g64 + p;
          const int c0 = table ? 0 : n >= 25 ? f_half : f_full + 64 * (q >> 3);
          const int c1 = table ? (2 * rb + ((n & 1) ^ 1)) * 128 + 64 * p : n >= 25 ? 128 * (n - 25) : 64 * (q & 7);
          const uint32_t fb = bars + 8 * (B_FA + (n & 3)), dst = sb + OFF_RING + (n & 3) * U + p * 8192;
          if (n < 4) mbar_wait(bars + 8 * (B_FE + n - 2), 0);
          else mbar_wait(bars + 8 * (B_EA + (n & 3)), ((n >> 2) & 1) ^ 1);
          tma2d(dst, m, fb, c0, c1);
          if (p == 0) mbar_expect_tx(fb, U);
        }
      } else if (warp == 15) {
        const unsigned ep1 = ld_x1(&g_epoch[blockIdx.x * 8]) + 1;
        flag_wait(&g_cntX[helper ? 0 : 32 * j], ep1 * 16u);
        PROF_EV(22);
        mbar_expect_tx(bars + 8 * B_HX, U);
        bulk_load(sb + OFF_XB, g_X + (size_t)(helper ? 128 : kg * 8 + tn) * 8192, U, bars + 8 * B_HX);
        if (!helper) {
          flag_wait(&g_cntT[32 * j], ep1 * 64u);
          PROF_EV(23);
          mbar_expect_tx(bars + 8 * B_TL, U);
          tma3d(sb + OFF_T, &maps.t, bars + 8 * B_TL, 64 * j, 0, 2 * rb);
#pragma unroll 1
          for (int i = 0; i < 3; i++) {
            mbar_wait(bars + 8 * (B_PZ + (i >> 1)), 0);
            flag_wait(&g_cntP[32 * (rb * 8 + j) + i], ep1 * 8u);
            mbar_expect_tx(bars + 8 * (B_HP + i), U);
            bulk_load(sb + i * U, g_part + (size_t)((rb * 8 + j) * 3 + i) * 1024, U, bars + 8 * (B_HP + i));
          }
          g_epoch[blockIdx.x * 8] = ep1;
        }
      } else {
#pragma unroll 1
        for (int q = 4; q < 8; q++) xf_load(q);
        mbar_wait(bars + 8 * (B_FE + 2), 0);
        mbar_expect_tx(bars + 8 * B_E0, U);
        tma2d(sb + OFF_XB, &maps.e, bars + 8 * B_E0, 0, 2 * rb * 128);
        tma2d(sb + OFF_XB + 8192, &maps.e, bars + 8 * B_E0, 0, 2 * rb * 128 + 64);
#pragma unroll 1
        for (int h2 = 0; h2 < 2; h2++) {
          const int s0 = 2 * rb + h2, sg = (s0 & ~6) | ((s0 & 2) << 1) | ((s0 & 4) >> 1);
          mbar_wait(bars + 8 * (B_XS + h2), 0);
#pragma unroll 1
          for (int c = 0; c < 2; c++) {
            asm volatile("cp.async.bulk.tensor.4d.global.shared::cta.bulk_group [%0, {%2, %3, %4, %5}], [%1];" ::"l"(&maps.xs),
                         "r"(sb + OFF_XB + h2 * 8192 + c * 4096), "r"(0), "r"(sg), "r"(0), "r"(16 * j + 8 * c) : "memory");
            if (j == 0)
              asm volatile("cp.async.bulk.global.shared::cta.bulk_group [%0], [%1], 256;" ::"l"(g_X + 128 * 8192 + c * 4096 + sg * 128),
                           "r"(sb + OFF_SP + h2 * 512 + c * 256) : "memory");
            if (SPACE && h2 + c < 2) __nanosleep(SPACE);
          }
        }
        bulk_done_signal(&g_cntX[32 * j]);
        PROF_EV(20);
#pragma unroll 1
        for (int t = 0; t < 8; t++) {
          const int i = t < 3 ? t + 1 : t < 6 ? t - 2 : 0;
          const int col = 64 * (2 * ((q4 + i) & 3) + ((t < 3 || t == 6) ? 1 - rank : rank));
          const uint32_t fb = bars + 8 * (B_FT + (t & 3)), dst = sb + (t & 3) * TB;
          mbar_wait(bars + 8 * (B_ET + (t == 2 ? 3 : t & 3)), t >> 2);
          mbar_expect_tx(fb, TB);
          tma2d(dst, &maps.d224, fb, col, 224 * j);
          if (t < 2) mbar_wait(bars + 8 * (B_ET + t + 1), 0);
          tma2d(dst + 28672, &maps.ft, fb, col, 64 * j);
        }
      }
    }
  }
}

typedef CUresult (*EncodeFn)(CUtensorMap*, CUtensorMapDataType, cuuint32_t, void*, const cuuint64_t*, const cuuint64_t*, const cuuint32_t*,
                             const cuuint32_t*, CUtensorMapInterleave, CUtensorMapSwizzle, CUtensorMapL2promotion, CUtensorMapFloatOOBfill);

static void encode(EncodeFn f, CUtensorMap* m, const void* base, int rank, const cuuint64_t* dims, const cuuint64_t* strides, const cuuint32_t* box,
                   CUtensorMapSwizzle sw) {
  cuuint32_t es[5] = {1, 1, 1, 1, 1};
  f(m, CU_TENSOR_MAP_DATA_TYPE_BFLOAT16, rank, (void*)base, dims, strides, box, es, CU_TENSOR_MAP_INTERLEAVE_NONE, sw,
    CU_TENSOR_MAP_L2_PROMOTION_L2_128B, CU_TENSOR_MAP_FLOAT_OOB_FILL_NONE);
}

extern "C" void kernel_launch(void* const* d_in, const int* in_sizes, int n_in, void* d_out, int out_size) {
  (void)in_sizes; (void)n_in; (void)out_size;
  const __nv_bfloat16* x = (const __nv_bfloat16*)d_in[0];
  const __nv_bfloat16* w_r = (const __nv_bfloat16*)d_in[1];
  const __nv_bfloat16* w_i = (const __nv_bfloat16*)d_in[2];
  const __nv_bfloat16* Wg = (const __nv_bfloat16*)d_in[4];
  const __nv_bfloat16* Wu = (const __nv_bfloat16*)d_in[5];
  const __nv_bfloat16* Wd = (const __nv_bfloat16*)d_in[6];
  const __nv_bfloat16* gw = (const __nv_bfloat16*)d_in[7];

  void* fp = nullptr; cudaDriverEntryPointQueryResult qr;
  cudaGetDriverEntryPoint("cuTensorMapEncodeTiled", &fp, cudaEnableDefault, &qr);
  EncodeFn enc = (EncodeFn)fp;
  void *pFT, *pET, *pX, *pT;
  cudaGetSymbolAddress(&pX, g_X); cudaGetSymbolAddress(&pT, g_T);
  cudaGetSymbolAddress(&pFT, g_FT); cudaGetSymbolAddress(&pET, g_ET);

  Maps mp;
  const CUtensorMapSwizzle S128 = CU_TENSOR_MAP_SWIZZLE_128B, S64 = CU_TENSOR_MAP_SWIZZLE_64B;
  { cuuint64_t d[3] = {512, 64, 32}, s[2] = {32768, 1024}; cuuint32_t b[3] = {64, 64, 2}; encode(enc, &mp.x, x, 3, d, s, b, S128); }
  { cuuint64_t d[2] = {512, 512}, s[1] = {1024}; cuuint32_t b[2] = {64, 64}; encode(enc, &mp.ft, pFT, 2, d, s, b, S128); }
  { cuuint64_t d[4] = {128, 32, 2, 129}, s[3] = {256, 8192, 16384}; cuuint32_t b[4] = {128, 1, 2, 8}; encode(enc, &mp.xs, pX, 4, d, s, b, CU_TENSOR_MAP_SWIZZLE_NONE); }
  { cuuint64_t d[3] = {512, 32, 64}, s[2] = {65536, 1024}; cuuint32_t b[3] = {32, 32, 2}; encode(enc, &mp.ts, pT, 3, d, s, b, S64); }
  { cuuint64_t d[3] = {512, 64, 32}, s[2] = {1024, 65536}; cuuint32_t b[3] = {64, 64, 2}; encode(enc, &mp.t, pT, 3, d, s, b, S128); }
  { cuuint64_t d[2] = {64, 4096}, s[1] = {128}; cuuint32_t b[2] = {64, 64}; encode(enc, &mp.e, pET, 2, d, s, b, S128); }
  { cuuint64_t d[2] = {1792, 512}, s[1] = {3584}; cuuint32_t b[2] = {64, 64}, b2[2] = {32, 128};
    encode(enc, &mp.g64, Wg, 2, d, s, b, S128); encode(enc, &mp.u64, Wu, 2, d, s, b, S128);
    encode(enc, &mp.g32, Wg, 2, d, s, b2, S64); encode(enc, &mp.u32, Wu, 2, d, s, b2, S64); }
  { cuuint64_t d[2] = {512, 1792}, s[1] = {1024}; cuuint32_t b[2] = {64, 224}; encode(enc, &mp.d224, Wd, 2, d, s, b, S128); }
  { cuuint64_t d[4] = {264, 32, 8, 8}, s[3] = {32896, 512, 4112}; cuuint32_t b[4] = {24, 32, 2, 1};
    encode(enc, &mp.wr, w_r, 4, d, s, b, CU_TENSOR_MAP_SWIZZLE_NONE); encode(enc, &mp.wi, w_i, 4, d, s, b, CU_TENSOR_MAP_SWIZZLE_NONE); }

  cudaFuncSetAttribute(fused_kernel, cudaFuncAttributeMaxDynamicSharedMemorySize, SMEM_BYTES);
  fused_kernel<<<NCTA, 512, SMEM_BYTES>>>(mp, w_r, w_i, gw, (__nv_bfloat16*)d_out);
}
```

```cpp
#include <cuda_runtime.h>
#include <cuda_bf16.h>
#include <cuda.h>
#include <stdint.h>

namespace tbl {
constexpr double PI = 3.14159265358979323846264338327950288;
constexpr double sin_s(double x) { double t = x, s = x; for (int n = 1; n < 12; n++) { t *= -x * x / ((2 * n) * (2 * n + 1)); s += t; } return s; }
constexpr double cos_s(double x) { double t = 1, s = 1; for (int n = 1; n < 12; n++) { t *= -x * x / ((2 * n - 1) * (2 * n)); s += t; } return s; }
constexpr double cos2048(int m) {
  m &= 2047; if (m > 1024) m = 2048 - m;
  bool neg = false; if (m > 512) { m = 1024 - m; neg = true; }
  double v = (m <= 256) ? cos_s(2 * PI * m / 2048) : sin_s(2 * PI * (512 - m) / 2048);
  return neg ? -v : v;
}
constexpr uint16_t to_bf16(double v) {
  if (v == 0) return 0;
  uint16_t s = 0; if (v < 0) { s = 0x8000; v = -v; }
  int e = 0; while (v >= 2) { v /= 2; e++; } while (v < 1) { v *= 2; e--; }
  double m = (v - 1) * 128; int mi = (int)m; double fr = m - mi;
  if (fr > 0.5 || (fr == 0.5 && (mi & 1))) mi++;
  if (mi == 128) { mi = 0; e++; }
  return (uint16_t)(s | ((e + 127) << 7) | mi);
}
struct CosT { uint16_t v[2048]; constexpr CosT() : v() { for (int i = 0; i < 2048; i++) v[i] = to_bf16(cos2048(i)); } };
struct alignas(1024) FT {
  uint16_t v[512 * 512];
  constexpr FT() : v() {
    CosT c;
    for (int r = 0; r < 512; r++) {
      int k = (r >> 4) * 8 + (r & 7), e = (r >> 3) & 1;
      int mul = 4 * k, add = e ? 512 : 0;
      if (k == 0 && e == 1) { mul = 1024; add = 0; }
      for (int d = 0; d < 512; d++) v[r * 512 + d] = c.v[(d * mul + add) & 2047];
    }
  }
};
struct alignas(1024) ET {
  uint16_t v[2048 * 128];
  constexpr ET() : v() {
    CosT c;
    for (int s = 0; s < 2048; s++)
      for (int j = 0; j < 64; j++) {
        const int o = (s & 31) * 8192 + (s >> 5) * 64 + j;
        v[o] = c.v[(s * j) & 2047]; v[o + 4096] = c.v[(s * j + 512) & 2047];
      }
  }
};
struct alignas(1024) DT {
  uint16_t v[64 * 64];
  constexpr DT() : v() {
    CosT c;
    for (int r = 0; r < 64; r++)
      for (int n = 0; n < 64; n++) {
        const int sg = r >> 1, s0 = (sg & ~6) | ((sg & 2) << 1) | ((sg & 4) >> 1), e = r & 1, f = n & 1;
        const int m = 64 * s0 * (n >> 1) + (e == f ? 0 : e ? -512 : 512);
        v[r * 64 + (((n >> 3) ^ (r & 7)) << 3) + (n & 7)] = c.v[m & 2047];
      }
  }
};
}

__device__ constexpr tbl::FT g_FT = tbl::FT();
__device__ constexpr tbl::ET g_ET = tbl::ET();
__device__ constexpr tbl::DT g_DT = tbl::DT();

__device__ __align__(1024) uint16_t g_X[129 * 8192];
__device__ __align__(1024) uint16_t g_T[32 * 64 * 512];
__device__ __align__(1024) uint2 g_Ts[32 * 64];
__device__ __align__(1024) uint4 g_part[128 * 3 * 1024];
__device__ __align__(16) float g_gate[16 * 128];
__device__ __align__(16) uint2 g_Wh[2 * 2048];
__device__ unsigned g_epoch[132 * 8];
__device__ unsigned g_cntX[8 * 32], g_cntT[8 * 32], g_cntP[128 * 32], g_cntW[32], g_cntH[32];
#define PROF_EV(i) do {} while (0)
#define PROF_CK(i) do {} while (0)

__device__ __forceinline__ uint32_t smem_u32(const void* p) { return (uint32_t)__cvta_generic_to_shared(p); }
__device__ __forceinline__ void mbar_init(uint32_t bar, uint32_t cnt) { asm volatile("mbarrier.init.shared::cta.b64 [%0], %1;" ::"r"(bar), "r"(cnt)); }
__device__ __forceinline__ void mbar_expect_tx(uint32_t bar, uint32_t bytes) { asm volatile("mbarrier.arrive.expect_tx.shared::cta.b64 _, [%0], %1;" ::"r"(bar), "r"(bytes) : "memory"); }
__device__ __forceinline__ void mbar_arrive(uint32_t bar) { asm volatile("mbarrier.arrive.shared::cta.b64 _, [%0];" ::"r"(bar) : "memory"); }
__device__ __forceinline__ bool elect_one() {
  uint32_t p;
  asm volatile("{\n.reg .pred p;\nelect.sync _|p, 0xffffffff;\nselp.u32 %0, 1, 0, p;\n}" : "=r"(p));
  return p;
}
__device__ __forceinline__ void mbar_arrive_if(bool p, uint32_t bar) {
  asm volatile("{\n.reg .pred p;\nsetp.ne.b32 p, %1, 0;\n@p mbarrier.arrive.shared::cta.b64 _, [%0];\n}" ::"r"(bar), "r"((int)p) : "memory");
}
__device__ __forceinline__ void hint_add_if(bool p, unsigned* a) {
  asm volatile("{\n.reg .pred p;\nsetp.ne.b32 p, %1, 0;\n@p red.relaxed.gpu.global.add.u32 [%0], 1;\n}" ::"l"(a), "r"((int)p) : "memory");
}
__device__ __forceinline__ bool mbar_try(uint32_t bar, uint32_t parity) {
  uint32_t ok;
  asm volatile("{\n.reg .pred p;\nmbarrier.test_wait.parity.shared::cta.b64 p, [%1], %2;\nselp.u32 %0, 1, 0, p;\n}" : "=r"(ok) : "r"(bar), "r"(parity) : "memory");
  return ok;
}
__device__ __forceinline__ void mbar_wait(uint32_t bar, uint32_t parity) {
  asm volatile(
      "{\n.reg .pred p;\n.reg .u32 n;\nmov.u32 n, 0;\n"
      "W_LOOP:\nmbarrier.try_wait.parity.shared::cta.b64 p, [%0], %1;\n@p bra W_DONE;\n"
      "add.u32 n, n, 1;\nsetp.lt.u32 p, n, 0x40000;\n@p bra W_LOOP;\ntrap;\nW_DONE:\n}" ::"r"(bar), "r"(parity) : "memory");
}
__device__ __forceinline__ void bulk_load(uint32_t dst, const void* src, uint32_t bytes, uint32_t bar) {
  asm volatile("cp.async.bulk.shared::cluster.global.mbarrier::complete_tx::bytes [%0], [%1], %2, [%3];" ::"r"(dst), "l"(src), "r"(bytes), "r"(bar) : "memory");
}
__device__ __forceinline__ void cp16(uint32_t dst, const void* src) { asm volatile("cp.async.cg.shared.global [%0], [%1], 16;" ::"r"(dst), "l"(src) : "memory"); }
__device__ __forceinline__ void spin_guard(uint32_t t0) { if ((uint32_t)clock() - t0 > (1u << 30)) __trap(); }
__device__ __forceinline__ float tagf(float v, uint32_t tag) { return __uint_as_float((__float_as_uint(v) & ~1u) | tag); }
__device__ __forceinline__ float untag(float v) { return __uint_as_float(__float_as_uint(v) & ~1u); }
__device__ __forceinline__ void st_x2(float2* p, float a, float b) { asm volatile("st.relaxed.gpu.global.v2.f32 [%0], {%1,%2};" ::"l"(p), "f"(a), "f"(b) : "memory"); }
__device__ __forceinline__ float2 ld_x2(const float2* p) { float2 v; asm volatile("ld.relaxed.gpu.global.v2.f32 {%0,%1}, [%2];" : "=f"(v.x), "=f"(v.y) : "l"(p) : "memory"); return v; }
__device__ __forceinline__ void st_u2(uint2* p, uint32_t a, uint32_t b) { asm volatile("st.relaxed.gpu.global.v2.u32 [%0], {%1,%2};" ::"l"(p), "r"(a), "r"(b) : "memory"); }
__device__ __forceinline__ void prefetch2d(const CUtensorMap* m, int c0, int c1) { asm volatile("cp.async.bulk.prefetch.tensor.2d.L2.global [%0, {%1, %2}];" ::"l"(m), "r"(c0), "r"(c1) : "memory"); }
__device__ __forceinline__ void prefetch1d(const void* p, uint32_t bytes) { asm volatile("cp.async.bulk.prefetch.L2.global [%0], %1;" ::"l"(p), "r"(bytes) : "memory"); }
__device__ __forceinline__ uint32_t ld_x1(const void* p) { uint32_t v; asm volatile("ld.relaxed.gpu.global.u32 %0, [%1];" : "=r"(v) : "l"(p) : "memory"); return v; }
__device__ __forceinline__ uint4 ld_x4(const void* p) { uint4 v; asm volatile("ld.relaxed.gpu.global.v4.u32 {%0,%1,%2,%3}, [%4];" : "=r"(v.x), "=r"(v.y), "=r"(v.z), "=r"(v.w) : "l"(p) : "memory"); return v; }
__device__ __forceinline__ void st_x4(void* p, uint32_t a, uint32_t b, uint32_t c, uint32_t d) { asm volatile("st.relaxed.gpu.global.v4.u32 [%0], {%1,%2,%3,%4};" ::"l"(p), "r"(a), "r"(b), "r"(c), "r"(d) : "memory"); }
__device__ __forceinline__ uint32_t mapa(uint32_t a, uint32_t cta) { uint32_t r; asm volatile("mapa.shared::cluster.u32 %0, %1, %2;" : "=r"(r) : "r"(a), "r"(cta)); return r; }
__device__ __forceinline__ void stsm4t(uint32_t a, uint32_t r0, uint32_t r1, uint32_t r2, uint32_t r3) {
  asm volatile("stmatrix.sync.aligned.m8n8.x4.trans.shared.b16 [%0], {%1,%2,%3,%4};" ::"r"(a), "r"(r0), "r"(r1), "r"(r2), "r"(r3) : "memory");
}
__device__ __forceinline__ void hint_add(unsigned* p) { asm volatile("red.relaxed.gpu.global.add.u32 [%0], 1;" ::"l"(p) : "memory"); }
__device__ __forceinline__ void hint_wait(const unsigned* p, unsigned target) {
  const uint32_t t0 = (uint32_t)clock();
  while ((int)(ld_x1(p) - target) < 0) spin_guard(t0);
}
__device__ __forceinline__ void bulk_done_signal(unsigned* p) {
  asm volatile("cp.async.bulk.commit_group;\ncp.async.bulk.wait_group 0;\nfence.proxy.async.global;" ::: "memory");
  hint_add(p);
}
__device__ __forceinline__ void flag_wait(const unsigned* p, unsigned target) {
  hint_wait(p, target);
  asm volatile("fence.proxy.async.global;" ::: "memory");
}
__device__ __forceinline__ void tma2d(uint32_t dst, const CUtensorMap* m, uint32_t bar, int c0, int c1) {
  asm volatile("cp.async.bulk.tensor.2d.shared::cluster.global.mbarrier::complete_tx::bytes [%0], [%1, {%3, %4}], [%2];" ::"r"(dst), "l"(m), "r"(bar), "r"(c0), "r"(c1) : "memory");
}
__device__ __forceinline__ void tma3d(uint32_t dst, const CUtensorMap* m, uint32_t bar, int c0, int c1, int c2) {
  asm volatile("cp.async.bulk.tensor.3d.shared::cluster.global.mbarrier::complete_tx::bytes [%0], [%1, {%3, %4, %5}], [%2];" ::"r"(dst), "l"(m), "r"(bar), "r"(c0), "r"(c1), "r"(c2) : "memory");
}
__device__ __forceinline__ void tma4d(uint32_t dst, const CUtensorMap* m, uint32_t bar, int c0, int c1, int c2, int c3) {
  asm volatile("cp.async.bulk.tensor.4d.shared::cluster.global.mbarrier::complete_tx::bytes [%0], [%1, {%3, %4, %5, %6}], [%2];" ::"r"(dst), "l"(m), "r"(bar), "r"(c0), "r"(c1), "r"(c2), "r"(c3) : "memory");
}
__device__ __forceinline__ void wg_fence() { asm volatile("wgmma.fence.sync.aligned;" ::: "memory"); }
__device__ __forceinline__ void wg_commit() { asm volatile("wgmma.commit_group.sync.aligned;" ::: "memory"); }
template <int N> __device__ __forceinline__ void wg_wait() { asm volatile("wgmma.wait_group.sync.aligned %0;" ::"n"(N) : "memory"); }
template <int O, int N, int NN> __device__ __forceinline__ void fence_regs(float (&d)[NN]) {
#pragma unroll
  for (int i = 0; i < N; i++) asm volatile("" : "+f"(d[O + i])::"memory");
}
__device__ __forceinline__ uint32_t pack_bf16(float lo, float hi) {
  uint32_t r; asm("cvt.rn.bf16x2.f32 %0, %1, %2;" : "=r"(r) : "f"(hi), "f"(lo)); return r;
}
__device__ __forceinline__ uint32_t pack_pin(float lo, float hi) {
  uint32_t r; asm volatile("cvt.rn.bf16x2.f32 %0, %1, %2;" : "=r"(r) : "f"(hi), "f"(lo) : "memory"); return r;
}
__device__ __forceinline__ float bf_lo(uint32_t u) { return __uint_as_float(u << 16); }
__device__ __forceinline__ float bf_hi(uint32_t u) { return __uint_as_float(u & 0xffff0000u); }

__device__ __forceinline__ uint64_t d128(uint32_t lo) { uint64_t d; asm("mov.b64 %0, {%1, 0x40000040};" : "=l"(d) : "r"(lo)); return d; }
__device__ __forceinline__ uint64_t d64(uint32_t lo) { uint64_t d; asm("mov.b64 %0, {%1, 0x80000020};" : "=l"(d) : "r"(lo)); return d; }
template<int O,int TB,int ACC,int NN> __device__ __forceinline__ void mma_ss64(float (&d)[NN], uint64_t da, uint64_t db, int sd = 0){
  if constexpr (ACC == 1) asm volatile("wgmma.mma_async.sync.aligned.m64n64k16.f32.bf16.bf16 {%0,%1,%2,%3,%4,%5,%6,%7,%8,%9,%10,%11,%12,%13,%14,%15,%16,%17,%18,%19,%20,%21,%22,%23,%24,%25,%26,%27,%28,%29,%30,%31}, %32, %33, 1, 1, 1, %35, %34;"
   : "+f"(d[O+0]), "+f"(d[O+1]), "+f"(d[O+2]), "+f"(d[O+3]), "+f"(d[O+4]), "+f"(d[O+5]), "+f"(d[O+6]), "+f"(d[O+7]), "+f"(d[O+8]), "+f"(d[O+9]), "+f"(d[O+10]), "+f"(d[O+11]), "+f"(d[O+12]), "+f"(d[O+13]), "+f"(d[O+14]), "+f"(d[O+15]), "+f"(d[O+16]), "+f"(d[O+17]), "+f"(d[O+18]), "+f"(d[O+19]), "+f"(d[O+20]), "+f"(d[O+21]), "+f"(d[O+22]), "+f"(d[O+23]), "+f"(d[O+24]), "+f"(d[O+25]), "+f"(d[O+26]), "+f"(d[O+27]), "+f"(d[O+28]), "+f"(d[O+29]), "+f"(d[O+30]), "+f"(d[O+31])
   : "l"(da), "l"(db), "n"(TB & 1), "n"(TB >> 1));
  else if constexpr (ACC == 0) asm volatile("wgmma.mma_async.sync.aligned.m64n64k16.f32.bf16.bf16 {%0,%1,%2,%3,%4,%5,%6,%7,%8,%9,%10,%11,%12,%13,%14,%15,%16,%17,%18,%19,%20,%21,%22,%23,%24,%25,%26,%27,%28,%29,%30,%31}, %32, %33, 0, 1, 1, %35, %34;"
   : "=f"(d[O+0]), "=f"(d[O+1]), "=f"(d[O+2]), "=f"(d[O+3]), "=f"(d[O+4]), "=f"(d[O+5]), "=f"(d[O+6]), "=f"(d[O+7]), "=f"(d[O+8]), "=f"(d[O+9]), "=f"(d[O+10]), "=f"(d[O+11]), "=f"(d[O+12]), "=f"(d[O+13]), "=f"(d[O+14]), "=f"(d[O+15]), "=f"(d[O+16]), "=f"(d[O+17]), "=f"(d[O+18]), "=f"(d[O+19]), "=f"(d[O+20]), "=f"(d[O+21]), "=f"(d[O+22]), "=f"(d[O+23]), "=f"(d[O+24]), "=f"(d[O+25]), "=f"(d[O+26]), "=f"(d[O+27]), "=f"(d[O+28]), "=f"(d[O+29]), "=f"(d[O+30]), "=f"(d[O+31])
   : "l"(da), "l"(db), "n"(TB & 1), "n"(TB >> 1));
  else asm volatile("{\n.reg .pred p;\nsetp.ne.b32 p, %36, 0;\nwgmma.mma_async.sync.aligned.m64n64k16.f32.bf16.bf16 {%0,%1,%2,%3,%4,%5,%6,%7,%8,%9,%10,%11,%12,%13,%14,%15,%16,%17,%18,%19,%20,%21,%22,%23,%24,%25,%26,%27,%28,%29,%30,%31}, %32, %33, p, 1, 1, %35, %34;\n}"
   : "+f"(d[O+0]), "+f"(d[O+1]), "+f"(d[O+2]), "+f"(d[O+3]), "+f"(d[O+4]), "+f"(d[O+5]), "+f"(d[O+6]), "+f"(d[O+7]), "+f"(d[O+8]), "+f"(d[O+9]), "+f"(d[O+10]), "+f"(d[O+11]), "+f"(d[O+12]), "+f"(d[O+13]), "+f"(d[O+14]), "+f"(d[O+15]), "+f"(d[O+16]), "+f"(d[O+17]), "+f"(d[O+18]), "+f"(d[O+19]), "+f"(d[O+20]), "+f"(d[O+21]), "+f"(d[O+22]), "+f"(d[O+23]), "+f"(d[O+24]), "+f"(d[O+25]), "+f"(d[O+26]), "+f"(d[O+27]), "+f"(d[O+28]), "+f"(d[O+29]), "+f"(d[O+30]), "+f"(d[O+31])
   : "l"(da), "l"(db), "n"(TB & 1), "n"(TB >> 1), "r"(sd));
}
template<int O,int TB,int ACC,int NN> __device__ __forceinline__ void mma_rs64(float (&d)[NN], uint32_t a0, uint32_t a1, uint32_t a2, uint32_t a3, uint64_t db, int sd = 0){
  if constexpr (ACC == 1) asm volatile("wgmma.mma_async.sync.aligned.m64n64k16.f32.bf16.bf16 {%0,%1,%2,%3,%4,%5,%6,%7,%8,%9,%10,%11,%12,%13,%14,%15,%16,%17,%18,%19,%20,%21,%22,%23,%24,%25,%26,%27,%28,%29,%30,%31}, {%32,%33,%34,%35}, %36, 1, 1, 1, %37;"
   : "+f"(d[O+0]), "+f"(d[O+1]), "+f"(d[O+2]), "+f"(d[O+3]), "+f"(d[O+4]), "+f"(d[O+5]), "+f"(d[O+6]), "+f"(d[O+7]), "+f"(d[O+8]), "+f"(d[O+9]), "+f"(d[O+10]), "+f"(d[O+11]), "+f"(d[O+12]), "+f"(d[O+13]), "+f"(d[O+14]), "+f"(d[O+15]), "+f"(d[O+16]), "+f"(d[O+17]), "+f"(d[O+18]), "+f"(d[O+19]), "+f"(d[O+20]), "+f"(d[O+21]), "+f"(d[O+22]), "+f"(d[O+23]), "+f"(d[O+24]), "+f"(d[O+25]), "+f"(d[O+26]), "+f"(d[O+27]), "+f"(d[O+28]), "+f"(d[O+29]), "+f"(d[O+30]), "+f"(d[O+31])
   : "r"(a0), "r"(a1), "r"(a2), "r"(a3), "l"(db), "n"(TB));
  else if constexpr (ACC == 0) asm volatile("wgmma.mma_async.sync.aligned.m64n64k16.f32.bf16.bf16 {%0,%1,%2,%3,%4,%5,%6,%7,%8,%9,%10,%11,%12,%13,%14,%15,%16,%17,%18,%19,%20,%21,%22,%23,%24,%25,%26,%27,%28,%29,%30,%31}, {%32,%33,%34,%35}, %36, 0, 1, 1, %37;"
   : "=f"(d[O+0]), "=f"(d[O+1]), "=f"(d[O+2]), "=f"(d[O+3]), "=f"(d[O+4]), "=f"(d[O+5]), "=f"(d[O+6]), "=f"(d[O+7]), "=f"(d[O+8]), "=f"(d[O+9]), "=f"(d[O+10]), "=f"(d[O+11]), "=f"(d[O+12]), "=f"(d[O+13]), "=f"(d[O+14]), "=f"(d[O+15]), "=f"(d[O+16]), "=f"(d[O+17]), "=f"(d[O+18]), "=f"(d[O+19]), "=f"(d[O+20]), "=f"(d[O+21]), "=f"(d[O+22]), "=f"(d[O+23]), "=f"(d[O+24]), "=f"(d[O+25]), "=f"(d[O+26]), "=f"(d[O+27]), "=f"(d[O+28]), "=f"(d[O+29]), "=f"(d[O+30]), "=f"(d[O+31])
   : "r"(a0), "r"(a1), "r"(a2), "r"(a3), "l"(db), "n"(TB));
  else asm volatile("{\n.reg .pred p;\nsetp.ne.b32 p, %38, 0;\nwgmma.mma_async.sync.aligned.m64n64k16.f32.bf16.bf16 {%0,%1,%2,%3,%4,%5,%6,%7,%8,%9,%10,%11,%12,%13,%14,%15,%16,%17,%18,%19,%20,%21,%22,%23,%24,%25,%26,%27,%28,%29,%30,%31}, {%32,%33,%34,%35}, %36, p, 1, 1, %37;\n}"
   : "+f"(d[O+0]), "+f"(d[O+1]), "+f"(d[O+2]), "+f"(d[O+3]), "+f"(d[O+4]), "+f"(d[O+5]), "+f"(d[O+6]), "+f"(d[O+7]), "+f"(d[O+8]), "+f"(d[O+9]), "+f"(d[O+10]), "+f"(d[O+11]), "+f"(d[O+12]), "+f"(d[O+13]), "+f"(d[O+14]), "+f"(d[O+15]), "+f"(d[O+16]), "+f"(d[O+17]), "+f"(d[O+18]), "+f"(d[O+19]), "+f"(d[O+20]), "+f"(d[O+21]), "+f"(d[O+22]), "+f"(d[O+23]), "+f"(d[O+24]), "+f"(d[O+25]), "+f"(d[O+26]), "+f"(d[O+27]), "+f"(d[O+28]), "+f"(d[O+29]), "+f"(d[O+30]), "+f"(d[O+31])
   : "r"(a0), "r"(a1), "r"(a2), "r"(a3), "l"(db), "n"(TB), "r"(sd));
}
template<int O,int TB,int ACC,int NN> __device__ __forceinline__ void mma_ss128(float (&d)[NN], uint64_t da, uint64_t db, int sd = 0){
  if constexpr (ACC == 1) asm volatile("wgmma.mma_async.sync.aligned.m64n128k16.f32.bf16.bf16 {%0,%1,%2,%3,%4,%5,%6,%7,%8,%9,%10,%11,%12,%13,%14,%15,%16,%17,%18,%19,%20,%21,%22,%23,%24,%25,%26,%27,%28,%29,%30,%31,%32,%33,%34,%35,%36,%37,%38,%39,%40,%41,%42,%43,%44,%45,%46,%47,%48,%49,%50,%51,%52,%53,%54,%55,%56,%57,%58,%59,%60,%61,%62,%63}, %64, %65, 1, 1, 1, %67, %66;"
   : "+f"(d[O+0]), "+f"(d[O+1]), "+f"(d[O+2]), "+f"(d[O+3]), "+f"(d[O+4]), "+f"(d[O+5]), "+f"(d[O+6]), "+f"(d[O+7]), "+f"(d[O+8]), "+f"(d[O+9]), "+f"(d[O+10]), "+f"(d[O+11]), "+f"(d[O+12]), "+f"(d[O+13]), "+f"(d[O+14]), "+f"(d[O+15]), "+f"(d[O+16]), "+f"(d[O+17]), "+f"(d[O+18]), "+f"(d[O+19]), "+f"(d[O+20]), "+f"(d[O+21]), "+f"(d[O+22]), "+f"(d[O+23]), "+f"(d[O+24]), "+f"(d[O+25]), "+f"(d[O+26]), "+f"(d[O+27]), "+f"(d[O+28]), "+f"(d[O+29]), "+f"(d[O+30]), "+f"(d[O+31]), "+f"(d[O+32]), "+f"(d[O+33]), "+f"(d[O+34]), "+f"(d[O+35]), "+f"(d[O+36]), "+f"(d[O+37]), "+f"(d[O+38]), "+f"(d[O+39]), "+f"(d[O+40]), "+f"(d[O+41]), "+f"(d[O+42]), "+f"(d[O+43]), "+f"(d[O+44]), "+f"(d[O+45]), "+f"(d[O+46]), "+f"(d[O+47]), "+f"(d[O+48]), "+f"(d[O+49]), "+f"(d[O+50]), "+f"(d[O+51]), "+f"(d[O+52]), "+f"(d[O+53]), "+f"(d[O+54]), "+f"(d[O+55]), "+f"(d[O+56]), "+f"(d[O+57]), "+f"(d[O+58]), "+f"(d[O+59]), "+f"(d[O+60]), "+f"(d[O+61]), "+f"(d[O+62]), "+f"(d[O+63])
   : "l"(da), "l"(db), "n"(TB & 1), "n"(TB >> 1));
  else if constexpr (ACC == 0) asm volatile("wgmma.mma_async.sync.aligned.m64n128k16.f32.bf16.bf16 {%0,%1,%2,%3,%4,%5,%6,%7,%8,%9,%10,%11,%12,%13,%14,%15,%16,%17,%18,%19,%20,%21,%22,%23,%24,%25,%26,%27,%28,%29,%30,%31,%32,%33,%34,%35,%36,%37,%38,%39,%40,%41,%42,%43,%44,%45,%46,%47,%48,%49,%50,%51,%52,%53,%54,%55,%56,%57,%58,%59,%60,%61,%62,%63}, %64, %65, 0, 1, 1, %67, %66;"
   : "=f"(d[O+0]), "=f"(d[O+1]), "=f"(d[O+2]), "=f"(d[O+3]), "=f"(d[O+4]), "=f"(d[O+5]), "=f"(d[O+6]), "=f"(d[O+7]), "=f"(d[O+8]), "=f"(d[O+9]), "=f"(d[O+10]), "=f"(d[O+11]), "=f"(d[O+12]), "=f"(d[O+13]), "=f"(d[O+14]), "=f"(d[O+15]), "=f"(d[O+16]), "=f"(d[O+17]), "=f"(d[O+18]), "=f"(d[O+19]), "=f"(d[O+20]), "=f"(d[O+21]), "=f"(d[O+22]), "=f"(d[O+23]), "=f"(d[O+24]), "=f"(d[O+25]), "=f"(d[O+26]), "=f"(d[O+27]), "=f"(d[O+28]), "=f"(d[O+29]), "=f"(d[O+30]), "=f"(d[O+31]), "=f"(d[O+32]), "=f"(d[O+33]), "=f"(d[O+34]), "=f"(d[O+35]), "=f"(d[O+36]), "=f"(d[O+37]), "=f"(d[O+38]), "=f"(d[O+39]), "=f"(d[O+40]), "=f"(d[O+41]), "=f"(d[O+42]), "=f"(d[O+43]), "=f"(d[O+44]), "=f"(d[O+45]), "=f"(d[O+46]), "=f"(d[O+47]), "=f"(d[O+48]), "=f"(d[O+49]), "=f"(d[O+50]), "=f"(d[O+51]), "=f"(d[O+52]), "=f"(d[O+53]), "=f"(d[O+54]), "=f"(d[O+55]), "=f"(d[O+56]), "=f"(d[O+57]), "=f"(d[O+58]), "=f"(d[O+59]), "=f"(d[O+60]), "=f"(d[O+61]), "=f"(d[O+62]), "=f"(d[O+63])
   : "l"(da), "l"(db), "n"(TB & 1), "n"(TB >> 1));
  else asm volatile("{\n.reg .pred p;\nsetp.ne.b32 p, %68, 0;\nwgmma.mma_async.sync.aligned.m64n128k16.f32.bf16.bf16 {%0,%1,%2,%3,%4,%5,%6,%7,%8,%9,%10,%11,%12,%13,%14,%15,%16,%17,%18,%19,%20,%21,%22,%23,%24,%25,%26,%27,%28,%29,%30,%31,%32,%33,%34,%35,%36,%37,%38,%39,%40,%41,%42,%43,%44,%45,%46,%47,%48,%49,%50,%51,%52,%53,%54,%55,%56,%57,%58,%59,%60,%61,%62,%63}, %64, %65, p, 1, 1, %67, %66;\n}"
   : "+f"(d[O+0]), "+f"(d[O+1]), "+f"(d[O+2]), "+f"(d[O+3]), "+f"(d[O+4]), "+f"(d[O+5]), "+f"(d[O+6]), "+f"(d[O+7]), "+f"(d[O+8]), "+f"(d[O+9]), "+f"(d[O+10]), "+f"(d[O+11]), "+f"(d[O+12]), "+f"(d[O+13]), "+f"(d[O+14]), "+f"(d[O+15]), "+f"(d[O+16]), "+f"(d[O+17]), "+f"(d[O+18]), "+f"(d[O+19]), "+f"(d[O+20]), "+f"(d[O+21]), "+f"(d[O+22]), "+f"(d[O+23]), "+f"(d[O+24]), "+f"(d[O+25]), "+f"(d[O+26]), "+f"(d[O+27]), "+f"(d[O+28]), "+f"(d[O+29]), "+f"(d[O+30]), "+f"(d[O+31]), "+f"(d[O+32]), "+f"(d[O+33]), "+f"(d[O+34]), "+f"(d[O+35]), "+f"(d[O+36]), "+f"(d[O+37]), "+f"(d[O+38]), "+f"(d[O+39]), "+f"(d[O+40]), "+f"(d[O+41]), "+f"(d[O+42]), "+f"(d[O+43]), "+f"(d[O+44]), "+f"(d[O+45]), "+f"(d[O+46]), "+f"(d[O+47]), "+f"(d[O+48]), "+f"(d[O+49]), "+f"(d[O+50]), "+f"(d[O+51]), "+f"(d[O+52]), "+f"(d[O+53]), "+f"(d[O+54]), "+f"(d[O+55]), "+f"(d[O+56]), "+f"(d[O+57]), "+f"(d[O+58]), "+f"(d[O+59]), "+f"(d[O+60]), "+f"(d[O+61]), "+f"(d[O+62]), "+f"(d[O+63])
   : "l"(da), "l"(db), "n"(TB & 1), "n"(TB >> 1), "r"(sd));
}
template<int O,int TB,int ACC,int NN> __device__ __forceinline__ void mma_rs128(float (&d)[NN], uint32_t a0, uint32_t a1, uint32_t a2, uint32_t a3, uint64_t db, int sd = 0){
  if constexpr (ACC == 1) asm volatile("wgmma.mma_async.sync.aligned.m64n128k16.f32.bf16.bf16 {%0,%1,%2,%3,%4,%5,%6,%7,%8,%9,%10,%11,%12,%13,%14,%15,%16,%17,%18,%19,%20,%21,%22,%23,%24,%25,%26,%27,%28,%29,%30,%31,%32,%33,%34,%35,%36,%37,%38,%39,%40,%41,%42,%43,%44,%45,%46,%47,%48,%49,%50,%51,%52,%53,%54,%55,%56,%57,%58,%59,%60,%61,%62,%63}, {%64,%65,%66,%67}, %68, 1, 1, 1, %69;"
   : "+f"(d[O+0]), "+f"(d[O+1]), "+f"(d[O+2]), "+f"(d[O+3]), "+f"(d[O+4]), "+f"(d[O+5]), "+f"(d[O+6]), "+f"(d[O+7]), "+f"(d[O+8]), "+f"(d[O+9]), "+f"(d[O+10]), "+f"(d[O+11]), "+f"(d[O+12]), "+f"(d[O+13]), "+f"(d[O+14]), "+f"(d[O+15]), "+f"(d[O+16]), "+f"(d[O+17]), "+f"(d[O+18]), "+f"(d[O+19]), "+f"(d[O+20]), "+f"(d[O+21]), "+f"(d[O+22]), "+f"(d[O+23]), "+f"(d[O+24]), "+f"(d[O+25]), "+f"(d[O+26]), "+f"(d[O+27]), "+f"(d[O+28]), "+f"(d[O+29]), "+f"(d[O+30]), "+f"(d[O+31]), "+f"(d[O+32]), "+f"(d[O+33]), "+f"(d[O+34]), "+f"(d[O+35]), "+f"(d[O+36]), "+f"(d[O+37]), "+f"(d[O+38]), "+f"(d[O+39]), "+f"(d[O+40]), "+f"(d[O+41]), "+f"(d[O+42]), "+f"(d[O+43]), "+f"(d[O+44]), "+f"(d[O+45]), "+f"(d[O+46]), "+f"(d[O+47]), "+f"(d[O+48]), "+f"(d[O+49]), "+f"(d[O+50]), "+f"(d[O+51]), "+f"(d[O+52]), "+f"(d[O+53]), "+f"(d[O+54]), "+f"(d[O+55]), "+f"(d[O+56]), "+f"(d[O+57]), "+f"(d[O+58]), "+f"(d[O+59]), "+f"(d[O+60]), "+f"(d[O+61]), "+f"(d[O+62]), "+f"(d[O+63])
   : "r"(a0), "r"(a1), "r"(a2), "r"(a3), "l"(db), "n"(TB));
  else if constexpr (ACC == 0) asm volatile("wgmma.mma_async.sync.aligned.m64n128k16.f32.bf16.bf16 {%0,%1,%2,%3,%4,%5,%6,%7,%8,%9,%10,%11,%12,%13,%14,%15,%16,%17,%18,%19,%20,%21,%22,%23,%24,%25,%26,%27,%28,%29,%30,%31,%32,%33,%34,%35,%36,%37,%38,%39,%40,%41,%42,%43,%44,%45,%46,%47,%48,%49,%50,%51,%52,%53,%54,%55,%56,%57,%58,%59,%60,%61,%62,%63}, {%64,%65,%66,%67}, %68, 0, 1, 1, %69;"
   : "=f"(d[O+0]), "=f"(d[O+1]), "=f"(d[O+2]), "=f"(d[O+3]), "=f"(d[O+4]), "=f"(d[O+5]), "=f"(d[O+6]), "=f"(d[O+7]), "=f"(d[O+8]), "=f"(d[O+9]), "=f"(d[O+10]), "=f"(d[O+11]), "=f"(d[O+12]), "=f"(d[O+13]), "=f"(d[O+14]), "=f"(d[O+15]), "=f"(d[O+16]), "=f"(d[O+17]), "=f"(d[O+18]), "=f"(d[O+19]), "=f"(d[O+20]), "=f"(d[O+21]), "=f"(d[O+22]), "=f"(d[O+23]), "=f"(d[O+24]), "=f"(d[O+25]), "=f"(d[O+26]), "=f"(d[O+27]), "=f"(d[O+28]), "=f"(d[O+29]), "=f"(d[O+30]), "=f"(d[O+31]), "=f"(d[O+32]), "=f"(d[O+33]), "=f"(d[O+34]), "=f"(d[O+35]), "=f"(d[O+36]), "=f"(d[O+37]), "=f"(d[O+38]), "=f"(d[O+39]), "=f"(d[O+40]), "=f"(d[O+41]), "=f"(d[O+42]), "=f"(d[O+43]), "=f"(d[O+44]), "=f"(d[O+45]), "=f"(d[O+46]), "=f"(d[O+47]), "=f"(d[O+48]), "=f"(d[O+49]), "=f"(d[O+50]), "=f"(d[O+51]), "=f"(d[O+52]), "=f"(d[O+53]), "=f"(d[O+54]), "=f"(d[O+55]), "=f"(d[O+56]), "=f"(d[O+57]), "=f"(d[O+58]), "=f"(d[O+59]), "=f"(d[O+60]), "=f"(d[O+61]), "=f"(d[O+62]), "=f"(d[O+63])
   : "r"(a0), "r"(a1), "r"(a2), "r"(a3), "l"(db), "n"(TB));
  else asm volatile("{\n.reg .pred p;\nsetp.ne.b32 p, %70, 0;\nwgmma.mma_async.sync.aligned.m64n128k16.f32.bf16.bf16 {%0,%1,%2,%3,%4,%5,%6,%7,%8,%9,%10,%11,%12,%13,%14,%15,%16,%17,%18,%19,%20,%21,%22,%23,%24,%25,%26,%27,%28,%29,%30,%31,%32,%33,%34,%35,%36,%37,%38,%39,%40,%41,%42,%43,%44,%45,%46,%47,%48,%49,%50,%51,%52,%53,%54,%55,%56,%57,%58,%59,%60,%61,%62,%63}, {%64,%65,%66,%67}, %68, p, 1, 1, %69;\n}"
   : "+f"(d[O+0]), "+f"(d[O+1]), "+f"(d[O+2]), "+f"(d[O+3]), "+f"(d[O+4]), "+f"(d[O+5]), "+f"(d[O+6]), "+f"(d[O+7]), "+f"(d[O+8]), "+f"(d[O+9]), "+f"(d[O+10]), "+f"(d[O+11]), "+f"(d[O+12]), "+f"(d[O+13]), "+f"(d[O+14]), "+f"(d[O+15]), "+f"(d[O+16]), "+f"(d[O+17]), "+f"(d[O+18]), "+f"(d[O+19]), "+f"(d[O+20]), "+f"(d[O+21]), "+f"(d[O+22]), "+f"(d[O+23]), "+f"(d[O+24]), "+f"(d[O+25]), "+f"(d[O+26]), "+f"(d[O+27]), "+f"(d[O+28]), "+f"(d[O+29]), "+f"(d[O+30]), "+f"(d[O+31]), "+f"(d[O+32]), "+f"(d[O+33]), "+f"(d[O+34]), "+f"(d[O+35]), "+f"(d[O+36]), "+f"(d[O+37]), "+f"(d[O+38]), "+f"(d[O+39]), "+f"(d[O+40]), "+f"(d[O+41]), "+f"(d[O+42]), "+f"(d[O+43]), "+f"(d[O+44]), "+f"(d[O+45]), "+f"(d[O+46]), "+f"(d[O+47]), "+f"(d[O+48]), "+f"(d[O+49]), "+f"(d[O+50]), "+f"(d[O+51]), "+f"(d[O+52]), "+f"(d[O+53]), "+f"(d[O+54]), "+f"(d[O+55]), "+f"(d[O+56]), "+f"(d[O+57]), "+f"(d[O+58]), "+f"(d[O+59]), "+f"(d[O+60]), "+f"(d[O+61]), "+f"(d[O+62]), "+f"(d[O+63])
   : "r"(a0), "r"(a1), "r"(a2), "r"(a3), "l"(db), "n"(TB), "r"(sd));
}

#define NEARLY 0
#define XAHEAD 3
#define HM 2
#define WBATCH 1
#define SPACE 0
#define WPF 1
#define WAFTER 7
#define WPACE 0
#define GATE_AT 4
#define TPACE 40
#define PFMODE 0
#define MAPMODE 0
template <int V> struct IC { static constexpr int value = V; };
struct Maps { CUtensorMap x, ft, g64, u64, e, wr, wi, xs, ts, t, g32, u32, d224; };

constexpr int NCTA = 130;
constexpr int U = 16384;
constexpr int TB = 36864;
constexpr int OFF_RING = 8 * U, OFF_Z = 9 * U, OFF_XB = 12 * U, OFF_T = 13 * U, OFF_D = OFF_T;
constexpr int OFF_BAR = 14 * U, OFF_SP = OFF_BAR + 512, OFF_G = OFF_SP + 1024 + 128;
constexpr int SMEM_BYTES = OFF_G + 512;
constexpr int B_FX = 0, B_FA = 8, B_FT = 12, B_Z = 16, B_W = 20, B_HX = 21, B_TL = 22, B_HP = 23, B_WR = 26, B_E0 = 30;
constexpr int B_EA = 31, B_ET = 35, B_PZ = 39, B_RDY = 41, B_FE = 42;
constexpr int B_T = 46, B_XS = 47, B_G = 49, NBAR = 50;
__host__ __device__ constexpr int rslot(int n) { return n & 3; }
__host__ __device__ constexpr int rpar(int n) { return (n >> 2) & 1; }

__global__ void __cluster_dims__(2, 1, 1) __launch_bounds__(512, 1)
fused_kernel(const __grid_constant__ Maps maps, const __nv_bfloat16* __restrict__ w_r,
             const __nv_bfloat16* __restrict__ w_i, const __nv_bfloat16* __restrict__ gate_w, __nv_bfloat16* __restrict__ out) {
  extern __shared__ __align__(1024) uint8_t smem[];
  const uint32_t sb = smem_u32(smem);
  const uint32_t bars = sb + OFF_BAR;
  const int tid = threadIdx.x, lane = tid & 31;
  const int warp = __shfl_sync(0xffffffffu, tid >> 5, 0);
  const bool helper = blockIdx.x >= 128;
  const int cl = (blockIdx.x >> 1) & 63, rank = blockIdx.x & 1;
  const int q4 = cl & 3, rb = cl >> 2;
  const int j = 2 * q4 + rank;
  const int f_full = 448 * q4 + (rank ? 256 : 0);
  const int f_half = 448 * q4 + (rank ? 224 : 192);
  const int kg = 2 * j + (rb >> 3), tn = rb & 7;

  if (tid == 64) { PROF_EV(0); PROF_CK(40); }
  if (warp < 8) {
    asm volatile("barrier.cluster.arrive.relaxed.aligned;" ::: "memory");
    asm volatile("setmaxnreg.inc.sync.aligned.u32 192;");
    if (!helper) {
      const int wg = warp >> 2, w = warp & 3, g = lane >> 2;
      const bool elect = (tid & 127) == 0;
      float cX[32], cA[64], cB[64], cC[64], ci[64], ct[64];
      const int zero = blockIdx.x >> 16;
      uint32_t h[56], yf[16];
      const uint32_t d0 = (sb & 0x3FFFF) >> 4;
      const uint32_t dK = d0 | (1u << 16), dN = d0 | (512u << 16);
      const uint32_t dX = dK + wg * 512;
      constexpr uint32_t RING = OFF_RING >> 4;
      auto waitA = [&](int n) { mbar_wait(bars + 8 * (B_FA + rslot(n)), rpar(n)); };
      auto freeA = [&](int n) { mbar_arrive_if(elect, bars + 8 * (B_EA + rslot(n))); };
      auto nop = [] {};

      asm volatile("bar.sync 0, 384;" ::: "memory");
#pragma unroll 1
      for (int i = 0; i < 4; i++) {
        const uint64_t dx = d128(dX + i * 2048), df = d128(dK + (OFF_XB >> 4) + (i & 1) * 1024);
        mbar_wait(bars + 8 * (B_FX + 2 * i), 0);
        wg_fence();
        mma_ss64<0, 0, 2>(cX, df, dx, i);
        mma_ss64<0, 0, 1>(cX, df + 2, dx + 2);
        wg_commit(); wg_wait<1>();
        mbar_arrive_if(elect && i, bars + 8 * (B_EA + rslot(i - 1)));
        mma_ss64<0, 0, 1>(cX, df + 4, dx + 4);
        mma_ss64<0, 0, 1>(cX, df + 6, dx + 6);
        if (i == 0 && tid == 0) PROF_EV(1);
        mbar_wait(bars + 8 * (B_FX + 2 * i + 1), 0);
        wg_fence();
#pragma unroll
        for (int k = 0; k < 4; k++) mma_ss64<0, 0, 1>(cX, df + (512 + k * 2), dx + (1024 + k * 2));
        wg_commit();
        waitA(i);
        wg_fence();
        const uint64_t da = d128(dX + i * 1024), db = d128(dN + RING + i * 1024);
        mma_ss128<0, 1, 2>(cA, da, db, i);
        wg_commit(); wg_wait<1>();
        mbar_arrive_if(elect, bars + 8 * (B_FE + i));
#pragma unroll
        for (int k = 1; k < 4; k++) mma_ss128<0, 1, 1>(cA, da + k * 2, db + k * 128);
        wg_commit();
      }
      fence_regs<0, 32>(cX);
#pragma unroll
      for (int e = 0; e < 16; e++) yf[e] = pack_pin(cX[2 * e], cX[2 * e + 1]);
      if (tid == 0) PROF_EV(2);
      {
        waitA(4); mbar_wait(bars + 8 * B_E0, 0);
        const uint64_t de = d128(dN + (wg ? RING : OFF_XB >> 4));
        wg_fence();
        mma_rs128<0, 1, 0>(cB, yf[0], yf[1], yf[2], yf[3], de);
        wg_commit();
        wg_wait<1>();
        freeA(3);
#pragma unroll
        for (int k = 1; k < 4; k++) mma_rs128<0, 1, 1>(cB, yf[4 * k], yf[4 * k + 1], yf[4 * k + 2], yf[4 * k + 3], de + k * 128);
        wg_commit();
      }
      bool rel = false;
      auto acquire = [&](int n) {
        rel = elect;
        if (!mbar_try(bars + 8 * (B_FA + rslot(n)), rpar(n))) { wg_wait<0>(); freeA(n - 1); rel = false; waitA(n); }
      };
      auto freeP = [&](int n) { mbar_arrive_if(rel, bars + 8 * (B_EA + rslot(n - 1))); };
      auto ffn_step = [&](auto first, auto split, float (&acc)[64], int n, int kb, auto done, auto work) {
        constexpr int SPLIT = decltype(split)::value;
        acquire(n);
        wg_fence();
        const uint64_t dx = d128(dX + kb * 1024), db = d128(dN + RING + rslot(n) * 1024);
        mma_ss128<0, 1, decltype(first)::value>(acc, dx, db, zero);
#pragma unroll
        for (int k = 1; k < SPLIT; k++) mma_ss128<0, 1, 1>(acc, dx + k * 2, db + k * 128);
        wg_commit();
        work();
        wg_wait<1>();
        freeP(n);
        done();
        if (SPLIT < 4) {
          wg_fence();
#pragma unroll
          for (int k = SPLIT; k < 4; k++) mma_ss128<0, 1, 1>(acc, dx + k * 2, db + k * 128);
          wg_commit();
        }
      };
      {
        const int s0 = 2 * rb + wg, kr = 2 * ((s0 & 1) | ((s0 & 4) >> 1));
        const int m = lane >> 3, r = lane & 7;
        const uint32_t a0 = sb + OFF_XB + wg * 8192 + (((w >> 1) * 8 + (m >> 1)) * 2 + (w & 1)) * 256 + (m & 1) * 128 + ((r ^ (kr + (m & 1))) << 4);
        ffn_step(IC<1>(), IC<4>(), cA, 5, 4, [&] { fence_regs<0, 64>(cB); }, nop);
        asm volatile("bar.sync 5, 256;" ::: "memory");
#pragma unroll
        for (int i = 0; i < 4; i++)
          stsm4t(a0 + i * 1024, pack_bf16(cB[8 * i] - cB[34 + 8 * i], cB[8 * i + 1] - cB[35 + 8 * i]),
                 pack_bf16(cB[32 + 8 * i] + cB[8 * i + 2], cB[33 + 8 * i] + cB[8 * i + 3]),
                 pack_bf16(cB[8 * i + 4] - cB[38 + 8 * i], cB[8 * i + 5] - cB[39 + 8 * i]),
                 pack_bf16(cB[36 + 8 * i] + cB[8 * i + 6], cB[37 + 8 * i] + cB[8 * i + 7]));
        if (j == 0 && w == 0) {
          const uint32_t a1 = r ? sb + OFF_SP + 1024 : sb + OFF_SP + wg * 512 + (m & 1) * 256 + (m >> 1) * 128;
#pragma unroll
          for (int n = 0; n < 8; n++)
            asm volatile("stmatrix.sync.aligned.m8n8.x4.shared.b16 [%0], {%1,%2,%3,%4};" ::"r"(a1 + ((n ^ (kr + (m >> 1))) << 4)),
                         "r"(pack_bf16(cB[4 * n], cB[4 * n + 1])), "r"(pack_bf16(cB[4 * n + 2], cB[4 * n + 3])),
                         "r"(pack_bf16(cB[32 + 4 * n], cB[33 + 4 * n])), "r"(pack_bf16(cB[34 + 4 * n], cB[35 + 4 * n])) : "memory");
        }
        ffn_step(IC<1>(), IC<2>(), cA, 6, 5, nop, [&] {
          asm volatile("fence.proxy.async.shared::cta;" ::: "memory");
          __syncwarp();
          mbar_arrive_if(lane == 0, bars + 8 * (B_XS + wg));
          if (tid == 0) PROF_EV(3);
        });
      }
#pragma unroll 1
      for (int kb = 6; kb < 8; kb++) ffn_step(IC<1>(), IC<1>(), cA, 1 + kb, kb, nop, nop);
      ffn_step(IC<2>(), IC<1>(), cB, 9, 0, [&] { fence_regs<0, 64>(cA); }, nop);
#pragma unroll 1
      for (int kb = 1; kb < 6; kb++) ffn_step(IC<1>(), IC<1>(), cB, 9 + kb, kb, nop, nop);
      mbar_wait(bars + 8 * B_G, 0);
      const uint32_t gb0 = *(const uint32_t*)(smem + OFF_G + (wg * 64 + w * 16 + g) * 4), gb1 = *(const uint32_t*)(smem + OFF_G + (wg * 64 + w * 16 + g + 8) * 4);
      const uint32_t tag = gb0 & 1;
      const float g0 = __uint_as_float(gb0 & ~1u), g1 = __uint_as_float(gb1 & ~1u);
      const float o0 = 1.0f - g0, o1 = 1.0f - g1;
      auto glu = [&](auto& acc, int half, int ho, int i0, int i1) {
#pragma unroll
        for (int i = i0; i < i1; i++) {
          const float o = (i & 1) ? o1 : o0;
          h[ho + i] = pack_pin(fmaxf(acc[2 * i], 0.f) * acc[half + 2 * i] * o, fmaxf(acc[2 * i + 1], 0.f) * acc[half + 1 + 2 * i] * o);
        }
      };
      ffn_step(IC<1>(), IC<1>(), cB, 15, 6, nop, [&] { glu(cA, 32, 0, 0, 8); });
      ffn_step(IC<1>(), IC<1>(), cB, 16, 7, nop, [&] { glu(cA, 32, 0, 8, 16); });
      ffn_step(IC<0>(), IC<1>(), cC, 17, 0, [&] { fence_regs<0, 64>(cB); }, nop);
      if (tid == 0) PROF_EV(4);
      ffn_step(IC<1>(), IC<1>(), cC, 18, 1, nop, [&] { glu(cB, 32, 16, 0, 8); });
      ffn_step(IC<1>(), IC<1>(), cC, 19, 2, nop, [&] { glu(cB, 32, 16, 8, 16); });
#pragma unroll 1
      for (int kb = 3; kb < 8; kb++) ffn_step(IC<1>(), IC<1>(), cC, 17 + kb, kb, nop, nop);
      if (tid == 0) PROF_EV(5);
      auto m_step = [&](auto first, int i, auto done, auto work) {
        acquire(25 + i);
        wg_fence();
        const uint64_t dx = d128(dX + i * 2048), dm = d64(dN + RING + rslot(25 + i) * 1024);
        mma_ss64<0, 1, decltype(first)::value>(ct, dx, dm);
        mma_ss64<0, 1, 1>(ct, dx + 2, dm + 64);
        wg_commit();
        work();
        wg_wait<1>();
        freeP(25 + i);
        done();
        wg_fence();
#pragma unroll
        for (int k = 2; k < 8; k++) mma_ss64<0, 1, 1>(ct, dx + ((k >> 2) * 1024 + (k & 3) * 2), dm + k * 64);
        wg_commit();
      };
      auto freeT = [&](int t) { mbar_arrive_if(elect, bars + 8 * (B_ET + t)); };
      m_step(IC<0>(), 0, [&] { fence_regs<0, 64>(cC); }, nop);
      m_step(IC<1>(), 1, [&] { freeT(0); }, [&] { glu(cC, 32, 32, 0, 5); });
      m_step(IC<1>(), 2, [&] { freeT(1); }, [&] { glu(cC, 32, 32, 5, 11); });
      m_step(IC<1>(), 3, [&] { freeT(2); }, [&] { glu(cC, 32, 32, 11, 16); });
      waitA(29 + wg);
      if (tid == 0) PROF_EV(6);
      mbar_wait(bars + 8 * (j == 0 ? B_T : B_TL), 0);
      if (tid == 0) PROF_EV(7);
      wg_fence();
      {
        const uint64_t dt = d128(dN + (OFF_T >> 4) + wg * 512), de = d128(dK + RING + (1 + wg) * 1024);
        mma_ss64<0, 1, 0>(ci, de, dt);
        mma_ss64<32, 1, 0>(ci, de + 512, dt);
#pragma unroll
        for (int k = 1; k < 4; k++) {
          mma_ss64<0, 1, 1>(ci, de + k * 2, dt + k * 128);
          mma_ss64<32, 1, 1>(ci, de + (512 + k * 2), dt + k * 128);
        }
        wg_commit();
        wg_wait<1>();
        freeT(3);
        fence_regs<0, 32>(ct);
        glu(ct, 16, 48, 0, 8);
      }

      auto head = [&](auto off, int t, auto first) {
        constexpr int O = decltype(off)::value;
        mbar_wait(bars + 8 * (B_FT + (t & 3)), t >> 2);
        const uint64_t db = d128(dN + (t & 3) * (TB >> 4) + rank * 256);
        wg_fence();
        mma_rs64<O, 1, decltype(first)::value>(ct, h[0], h[1], h[2], h[3], db, zero);
#pragma unroll
        for (int k = 1; k < 6; k++) mma_rs64<O, 1, 1>(ct, h[4 * k], h[4 * k + 1], h[4 * k + 2], h[4 * k + 3], db + k * 128);
        wg_commit();
        wg_wait<1>();
      };
      auto rest = [&](auto off, int t) {
        constexpr int O = decltype(off)::value;
        const uint64_t db = d128(dN + (t & 3) * (TB >> 4)), dw = db + rank * 256, dm = db + (rank ? 0 : 1536);
        wg_fence();
#pragma unroll
        for (int k = 6; k < 12; k++) mma_rs64<O, 1, 1>(ct, h[4 * k], h[4 * k + 1], h[4 * k + 2], h[4 * k + 3], dw + k * 128);
#pragma unroll
        for (int k = 0; k < 2; k++) mma_rs64<O, 1, 1>(ct, h[48 + 4 * k], h[49 + 4 * k], h[50 + 4 * k], h[51 + 4 * k], dm + k * 128);
#pragma unroll
        for (int k = 0; k < 4; k++) mma_rs64<O, 1, 1>(ct, yf[4 * k], yf[4 * k + 1], yf[4 * k + 2], yf[4 * k + 3], db + (14 + k) * 128);
        wg_commit();
      };
      const uint32_t peerZ = mapa(sb + OFF_Z + tid * 16, rank ^ 1), peerB = mapa(bars + 8 * B_Z, rank ^ 1);
      auto send = [&](auto off, int t) {
        constexpr int O = decltype(off)::value;
        fence_regs<O, 32>(ct);
        const bool grid = t >= 3 && t < 6;
        const int z = grid ? t - 3 : t == 6 ? 3 : t;
        if (grid) {
          mbar_wait(bars + 8 * (B_Z + z), 0);
#pragma unroll
          for (int i = 0; i < 4; i++) {
            const uint4 p = *(const uint4*)(smem + OFF_Z + z * U + i * 4096 + tid * 16);
            const uint32_t a[4] = {p.x, p.y, p.z, p.w};
#pragma unroll
            for (int e = 0; e < 4; e++) { ct[O + 8 * i + 2 * e] += bf_lo(a[e]); ct[O + 8 * i + 2 * e + 1] += bf_hi(a[e]); }
          }
        }
        uint32_t pk[16];
#pragma unroll
        for (int i = 0; i < 16; i++) pk[i] = pack_bf16(ct[O + 2 * i], ct[O + 2 * i + 1]);
        if (grid) {
          const int owner = rb * 8 + 2 * ((q4 + z + 1) & 3) + rank;
          uint4* dst = g_part + (size_t)(owner * 3 + z) * 1024 + tid;
#pragma unroll
          for (int i = 0; i < 4; i++) st_x4(dst + i * 256, (pk[4 * i] & ~1u) | tag, pk[4 * i + 1], pk[4 * i + 2], pk[4 * i + 3]);
          __syncwarp();
          hint_add_if(lane == 0, &g_cntP[32 * owner + z]);
        } else {
#pragma unroll
          for (int i = 0; i < 4; i++)
            asm volatile("st.async.weak.shared::cluster.mbarrier::complete_tx::bytes.v4.b32 [%0], {%1,%2,%3,%4}, [%5];" ::"r"(peerZ + z * U + i * 4096),
                         "r"(pk[4 * i]), "r"(pk[4 * i + 1]), "r"(pk[4 * i + 2]), "r"(pk[4 * i + 3]), "r"(peerB + 8 * z) : "memory");
        }
      };
      asm volatile("barrier.cluster.wait.aligned;" ::: "memory");
      head(IC<0>(), 0, IC<2>());
      if (elect) asm volatile("mbarrier.arrive.shared::cluster.b64 _, [%0];" ::"r"(mapa(bars + 8 * B_RDY, rank ^ 1)) : "memory");
      fence_regs<0, 64>(ci);
#pragma unroll
      for (int i = 0; i < 16; i++) {
        const float gg = ((i & 1) ? g1 : g0) * (2.0f / (2048.0f * 512.0f));
        if (i & 2) yf[i] = pack_pin((ci[2 * i] - ci[28 + 2 * i]) * gg, (ci[2 * i + 1] - ci[29 + 2 * i]) * gg);
        else yf[i] = pack_pin((ci[2 * i] + ci[36 + 2 * i]) * gg, (ci[2 * i + 1] + ci[37 + 2 * i]) * gg);
      }
      if (tid == 0) PROF_EV(8);
#pragma unroll 1
      for (int t = 0;; t += 2) {
        rest(IC<0>(), t);
        head(IC<32>(), t + 1, IC<2>());
        mbar_arrive_if(elect && t < 6, bars + 8 * (B_ET + t));
        if (t == 0) mbar_wait(bars + 8 * B_RDY, 0);
        send(IC<0>(), t);
        rest(IC<32>(), t + 1);
        if (t == 6) break;
        head(IC<0>(), t + 2, IC<2>());
        mbar_arrive_if(elect, bars + 8 * (B_ET + t + 1));
        if (t == 4 && tid == 0) PROF_EV(27);
        send(IC<32>(), t + 1);
        if (t == 4 && tid == 0) PROF_EV(25);
      }
      if (tid == 0) PROF_EV(9);
      {
        float sum[32];
        mbar_wait(bars + 8 * (B_Z + 3), 0);
#pragma unroll
        for (int i = 0; i < 4; i++) {
          const uint4 p = *(const uint4*)(smem + OFF_Z + 3 * U + i * 4096 + tid * 16);
          const uint32_t a[4] = {p.x, p.y, p.z, p.w};
#pragma unroll
          for (int e = 0; e < 4; e++) { sum[8 * i + 2 * e] = bf_lo(a[e]); sum[8 * i + 2 * e + 1] = bf_hi(a[e]); }
        }
#pragma unroll 1
        for (int z = 0; z < 3; z++) {
          mbar_wait(bars + 8 * (B_HP + z), 0);
          if (z == 2 && tid == 0) PROF_EV(24);
          uint4 pv[4];
#pragma unroll
          for (int i = 0; i < 4; i++) pv[i] = *(const uint4*)(smem + z * U + i * 4096 + tid * 16);
          const uint32_t t0 = (uint32_t)clock();
          while (__any_sync(0xffffffffu, ((pv[0].x ^ tag) | (pv[1].x ^ tag) | (pv[2].x ^ tag) | (pv[3].x ^ tag)) & 1)) {
#pragma unroll
            for (int i = 0; i < 4; i++) pv[i] = ld_x4(g_part + (size_t)((rb * 8 + j) * 3 + z) * 1024 + tid + i * 256);
            spin_guard(t0);
          }
#pragma unroll
          for (int i = 0; i < 4; i++) {
            const uint32_t a[4] = {pv[i].x & ~1u, pv[i].y, pv[i].z, pv[i].w};
#pragma unroll
            for (int e = 0; e < 4; e++) { sum[8 * i + 2 * e] += bf_lo(a[e]); sum[8 * i + 2 * e + 1] += bf_hi(a[e]); }
          }
        }
        if (tid == 0) PROF_EV(14);
        wg_wait<0>();
        fence_regs<32, 32>(ct);
#pragma unroll
        for (int i = 0; i < 32; i++) sum[i] += ct[32 + i];
        const uint32_t stg = sb + OFF_T + warp * 2048;
        const int mr = (lane & 7) + ((lane >> 3) & 1) * 8, mc = lane >> 4;
#pragma unroll
        for (int i = 0; i < 4; i++) {
          const uint32_t a = stg + mr * 128 + (((2 * i + mc) ^ (mr & 7)) << 4);
          asm volatile("stmatrix.sync.aligned.m8n8.x4.shared.b16 [%0], {%1,%2,%3,%4};" ::"r"(a), "r"(pack_bf16(sum[8 * i], sum[8 * i + 1])),
                       "r"(pack_bf16(sum[8 * i + 2], sum[8 * i + 3])), "r"(pack_bf16(sum[8 * i + 4], sum[8 * i + 5])),
                       "r"(pack_bf16(sum[8 * i + 6], sum[8 * i + 7])) : "memory");
        }
        __syncwarp();
#pragma unroll
        for (int i = 0; i < 4; i++) {
          const int r = 4 * i + (lane >> 3), c = lane & 7;
          const uint4 v = *(const uint4*)(smem + OFF_T + warp * 2048 + r * 128 + ((c ^ (r & 7)) << 4));
          *(uint4*)(out + (size_t)(2 * rb + wg + 32 * (16 * w + r)) * 512 + 64 * j + 8 * c) = v;
        }
      }
      if (tid == 0) { PROF_EV(15); PROF_CK(41); }
    }
  } else if (warp < 12) {
    asm volatile("setmaxnreg.dec.sync.aligned.u32 104;");
    asm volatile("barrier.cluster.arrive.relaxed.aligned;" ::: "memory");
    const int t = tid - 256, w = warp - 8;
    const uint32_t ep = ld_x1(&g_epoch[blockIdx.x * 8]);
    const uint32_t tag = (ep + 1) & 1;
    auto w_issue = [&](const CUtensorMap* m) {
          if (elect_one()) { mbar_expect_tx(bars + 8 * (B_WR + w), 3072); tma4d(sb + OFF_T + w * 3072, m, bars + 8 * (B_WR + w), 16 * kg, 0, 2 * w, tn); }
          __syncwarp();
    };
    auto gate_rows = [&] {
      const int r = 16 * j + 4 * w + (lane >> 3);
      const uint4* pg = (const uint4*)gate_w + (lane & 7);
      {
        float a = 0.f;
        asm volatile("bar.sync 4, 256;" ::: "memory");
#pragma unroll 1
        for (int hf = 0; hf < 2; hf++) {
          uint4 v[4], u[4];
#pragma unroll
          for (int kb = 0; kb < 4; kb++) v[kb] = __ldg(pg + (4 * hf + kb) * 8);
          mbar_wait(bars + 8 * (B_FE + 1 + 2 * hf), 0);
          if (hf) w_issue(&maps.wr);
#pragma unroll
          for (int kb = 0; kb < 4; kb++) u[kb] = *(const uint4*)(smem + (4 * hf + kb) * U + r * 128 + (((lane ^ r) & 7) << 4));
#pragma unroll
          for (int kb = 0; kb < 4; kb++) {
            a = fmaf(bf_lo(u[kb].x), bf_lo(v[kb].x), a); a = fmaf(bf_hi(u[kb].x), bf_hi(v[kb].x), a);
            a = fmaf(bf_lo(u[kb].y), bf_lo(v[kb].y), a); a = fmaf(bf_hi(u[kb].y), bf_hi(v[kb].y), a);
            a = fmaf(bf_lo(u[kb].z), bf_lo(v[kb].z), a); a = fmaf(bf_hi(u[kb].z), bf_hi(v[kb].z), a);
            a = fmaf(bf_lo(u[kb].w), bf_lo(v[kb].w), a); a = fmaf(bf_hi(u[kb].w), bf_hi(v[kb].w), a);
          }
        }
#pragma unroll
        for (int o = 4; o; o >>= 1) a += __shfl_xor_sync(0xffffffffu, a, o);
        if ((lane & 7) == 0)
          asm volatile("st.relaxed.gpu.global.f32 [%0], %1;" ::"l"(g_gate + rb * 128 + r), "f"(tagf(__fdividef(1.0f, 1.0f + __expf(-a)), tag)) : "memory");
        if (t == 0) PROF_EV(18);
      }
    };
    {
      const int g = lane >> 2, q = lane & 3;
      uint32_t wf[32];
      if (!helper) {
        gate_rows();
        const uint32_t wa = sb + OFF_T + w * (3072 + 4) + q * 48 + g * 2;
#pragma unroll 1
        for (int ri = 0; ri < 2; ri++) {
          mbar_wait(bars + 8 * (B_WR + w), ri);
#pragma unroll
          for (int n2 = 0; n2 < 2; n2++) {
            uint32_t v[16];
#pragma unroll
            for (int i = 0; i < 16; i++)
              asm volatile("ld.shared.u16 %0, [%1];" : "=r"(v[i]) : "r"(wa + (4 * n2 + ((i >> 1) & 3)) * 192 + (i & 1) * (1536 + 2) + (i >> 3) * 16) : "memory");
#pragma unroll
            for (int i = 0; i < 16; i++) {
              uint32_t& d = wf[(i >> 3) * 16 + 8 * n2 + (i & 7)];
              d = __byte_perm(d, v[i], 0x5432);
              asm volatile("" : "+r"(d)::"memory");
            }
          }
          __syncwarp();
          if (ri == 0) w_issue(&maps.wi);
        }
        asm volatile("bar.sync 1, 128;" ::: "memory");
        if (t == 0) PROF_EV(11);
      } else {
        asm volatile("bar.sync 4, 256;" ::: "memory");
        hint_wait(&g_cntW[0], (ep + 1) * 128u);
        const uint32_t t0 = (uint32_t)clock();
#pragma unroll 1
        for (;;) {
          uint32_t bad = 0;
#pragma unroll
          for (int i = 0; i < 32; i++) {
            const float2 v = ld_x2((const float2*)g_Wh + (i >> 4) * 2048 + 16 * w + g + 8 * (i & 1) + 64 * q + ((i >> 1) & 7) * 256);
            wf[i] = __float_as_uint(v.x); bad |= __float_as_uint(v.y) ^ tag;
          }
          if (!__any_sync(0xffffffffu, bad & 1)) break;
          spin_guard(t0);
        }
        if (t == 0) PROF_EV(11);
      }
      if (w == 0 && elect_one()) { mbar_expect_tx(bars + 8 * B_W, 8192); bulk_load(sb + OFF_D, g_DT.v, 8192, bars + 8 * B_W); }
      if (!helper) {
        const uint32_t t0 = (uint32_t)clock();
        uint32_t v;
        do { v = ld_x1(g_gate + rb * 128 + t); spin_guard(t0); } while (__any_sync(0xffffffffu, (v ^ tag) & 1));
        *(uint32_t*)(smem + OFF_G + t * 4) = v;
        __syncwarp();
        mbar_arrive_if(lane == 0, bars + 8 * B_G);
      }
      mbar_wait(bars + 8 * B_W, 0);
      mbar_wait(bars + 8 * B_HX, 0);
      if (t == 0) PROF_EV(12);
      const uint32_t dd = (sb & 0x3FFFF) >> 4;
      const uint64_t dF = d128((dd + (OFF_D >> 4)) | (512u << 16)), dI = d128((dd + (OFF_D >> 4)) | (1u << 16)), dA = d128((dd + (OFF_XB >> 4)) | (512u << 16));
      float az[32];
      const int zero = blockIdx.x >> 16;
      uint32_t pf[32];
#pragma unroll
      for (int mt = 0; mt < 2; mt++) {
        wg_fence();
        if (mt == 0) mma_ss64<0, 3, 0>(az, dA, dF);
        else mma_ss64<0, 3, 2>(az, dA + 512, dF, zero);
#pragma unroll
        for (int k = 1; k < 4; k++) mma_ss64<0, 3, 1>(az, dA + (mt * 512 + k * 128), dF + k * 128);
        wg_commit();
        wg_wait<0>();
        fence_regs<0, 32>(az);
#pragma unroll
        for (int i = 0; i < 16; i++) {
          const float wr = bf_lo(wf[16 * mt + i]), wi = bf_hi(wf[16 * mt + i]);
          pf[16 * mt + i] = pack_pin(fmaf(az[2 * i], wr, -az[2 * i + 1] * wi), fmaf(az[2 * i], wi, az[2 * i + 1] * wr));
        }
      }
      if (t == 0) PROF_EV(16);
#pragma unroll
      for (int mt = 0; mt < 2; mt++) {
        wg_fence();
        mma_rs64<0, 0, 2>(az, pf[16 * mt], pf[16 * mt + 1], pf[16 * mt + 2], pf[16 * mt + 3], dI, mt ? (int)helper : zero);
#pragma unroll
        for (int k = 1; k < 4; k++) mma_rs64<0, 0, 1>(az, pf[16 * mt + 4 * k], pf[16 * mt + 4 * k + 1], pf[16 * mt + 4 * k + 2], pf[16 * mt + 4 * k + 3], dI + k * 2);
        wg_commit();
        wg_wait<0>();
        fence_regs<0, 32>(az);
        if (!helper) {
          const int m = lane >> 3, r = lane & 7;
          const int sl = 2 * (m >> 1) + ((r >> 1) & 1) + 4 * (r >> 2);
          const uint32_t a0 = sb + OFF_XB + (2 * w + (m & 1)) * 2048 + sl * 64 + (((mt * 2 + (r & 1)) ^ (sl >> 1)) << 4);
#pragma unroll
          for (int i = 0; i < 4; i++)
            stsm4t(a0 + i * 512, pack_bf16(az[8 * i], az[8 * i + 1]), pack_bf16(az[8 * i + 2], az[8 * i + 3]), pack_bf16(az[8 * i + 4], az[8 * i + 5]),
                   pack_bf16(az[8 * i + 6], az[8 * i + 7]));
        }
      }
      if (helper) {
#pragma unroll
        for (int i = 0; i < 16; i++) {
          const int n = i >> 1, s0 = 8 * (n >> 1) + 2 * (n & 1) + (q & 1) + 4 * (q >> 1);
          if ((n & 1) == (int)(blockIdx.x & 1)) st_u2(g_Ts + s0 * 64 + 16 * w + g + 8 * (i & 1), pack_bf16(az[2 * i], az[2 * i + 1]), tag);
        }
        __syncwarp();
        hint_add_if(lane == 0, &g_cntH[0]);
        if (t == 0) { g_epoch[blockIdx.x * 8] = ep + 1; PROF_EV(13); }
      } else {
        asm volatile("fence.proxy.async.shared::cta;" ::: "memory");
        __syncwarp();
        if (elect_one()) {
          if (t == 0) PROF_EV(17);
          if (SPACE) __nanosleep(SPACE * w);
          asm volatile("cp.async.bulk.tensor.3d.global.shared::cta.bulk_group [%0, {%2, %3, %4}], [%1];" ::"l"(&maps.ts), "r"(sb + OFF_XB + w * 4096),
                       "r"(32 * kg), "r"(0), "r"(8 * tn + 2 * w) : "memory");
          bulk_done_signal(&g_cntT[32 * j]);
          if (t == 96) PROF_EV(13);
        }
        __syncwarp();
        if (j == 0) {
          hint_wait(&g_cntH[0], (ep + 1) * 8u);
          const uint32_t t0 = (uint32_t)clock();
          float2 v;
          do { v = ld_x2((const float2*)g_Ts + 2 * rb * 64 + t); spin_guard(t0); } while (__any_sync(0xffffffffu, (__float_as_uint(v.y) ^ tag) & 1));
          mbar_wait(bars + 8 * B_TL, 0);
          const uint32_t u = __float_as_uint(v.x);
          *(uint16_t*)(smem + OFF_T + t * 128 + ((t & 7) << 4)) = (uint16_t)u;
          *(uint16_t*)(smem + OFF_T + t * 128 + (((t & 7) ^ 1) << 4)) = (uint16_t)(u >> 16);
          asm volatile("fence.proxy.async.shared::cta;" ::: "memory");
          __syncwarp();
          mbar_arrive_if(lane == 0, bars + 8 * B_T);
        }
      }
    }
  } else {
    asm volatile("setmaxnreg.dec.sync.aligned.u32 24;");
    auto xf_load = [&](int q) {
      const uint32_t fb = bars + 8 * (B_FX + q);
      mbar_expect_tx(fb, U + 8192);
      tma3d(sb + q * U, &maps.x, fb, 64 * q, 0, 2 * rb);
      if (q >= 4) mbar_wait(bars + 8 * (B_FE + ((q - 4) >> 1)), 0);
      tma2d(sb + OFF_XB + (q & 3) * 8192, &maps.ft, fb, 64 * q, 64 * j);
    };
    if (elect_one()) {
      if (warp == 14) {
#pragma unroll
        for (int i = 0; i < B_FT; i++) mbar_init(bars + 8 * i, 1);
        asm volatile("fence.proxy.async.shared::cta;" ::: "memory");
        if (!helper) {
#pragma unroll 1
          for (int n = 0; n < 2; n++) {
            const uint32_t fb = bars + 8 * (B_FA + n);
            xf_load(2 * n); xf_load(2 * n + 1);
            mbar_expect_tx(fb, U);
            tma2d(sb + OFF_RING + n * U, &maps.g64, fb, f_full, 64 * n);
            tma2d(sb + OFF_RING + n * U + 8192, &maps.u64, fb, f_full, 64 * n);
          }
        }
      } else if (warp == 15) {
#pragma unroll
        for (int i = B_FT; i < NBAR; i++) mbar_init(bars + 8 * i, i < B_EA ? 1 : i < B_T ? 2 : 4);
#pragma unroll
        for (int i = 0; i < 4; i++) mbar_expect_tx(bars + 8 * (B_Z + i), U);
        asm volatile("fence.mbarrier_init.release.cluster;" ::: "memory");
        asm volatile("fence.proxy.async.shared::cta;" ::: "memory");
      } else if (warp == 13) {
#pragma unroll
        for (int i = 1; i < 4; i++) asm volatile("prefetch.tensormap [%0];" ::"l"((const char*)&maps + i * 128) : "memory");
      }
    }
    __syncwarp();
    asm volatile("bar.arrive 0, 384;" ::: "memory");
    asm volatile("bar.arrive 4, 256;" ::: "memory");
    __syncwarp();
    asm volatile("barrier.cluster.arrive.relaxed.aligned;" ::: "memory");
    asm volatile("bar.sync 3, 128;" ::: "memory");
    if (warp == 15 && !helper) {
        mbar_wait(bars + 8 * B_FE, 0);
        const uint32_t tag = (ld_x1(&g_epoch[blockIdx.x * 8]) + 1) & 1;
        const int c = lane >> 4, jj = 16 * blockIdx.x + (lane & 15), jm = (2048 - jj) & 2047;
        const unsigned short* pr = (const unsigned short*)w_r + 256 * c;
        const unsigned short* pi = (const unsigned short*)w_i + 256 * c;
        const float wr = 0.25f * (bf_lo(__ldg(pr + jj * 257)) + bf_lo(__ldg(pr + jm * 257)));
        const float wi = 0.25f * (bf_lo(__ldg(pi + jj * 257)) - bf_lo(__ldg(pi + jm * 257)));
        st_u2(g_Wh + c * 2048 + jj, c ? pack_bf16(-wi, wr) : pack_bf16(wr, wi), tag);
        __syncwarp();
        hint_add_if(lane == 0, &g_cntW[0]);
      }
    if ((!helper || warp == 15) && elect_one()) {
      if (warp < 14) {
        const int p = warp - 12;
#pragma unroll 1
        for (int n = 2; n < 31; n++) {
          const bool table = n == 4 || n >= 29;
          const int q = n < 4 ? n : n - 1;
          const CUtensorMap* m = table ? &maps.e : n >= 25 ? &maps.g32 + p : &maps.g64 + p;
          const int c0 = table ? 0 : n >= 25 ? f_half : f_full + 64 * (q >> 3);
          const int c1 = table ? (2 * rb + ((n & 1) ^ 1)) * 128 + 64 * p : n >= 25 ? 128 * (n - 25) : 64 * (q & 7);
          const uint32_t fb = bars + 8 * (B_FA + (n & 3)), dst = sb + OFF_RING + (n & 3) * U + p * 8192;
          if (n < 4) mbar_wait(bars + 8 * (B_FE + n - 2), 0);
          else mbar_wait(bars + 8 * (B_EA + (n & 3)), ((n >> 2) & 1) ^ 1);
          tma2d(dst, m, fb, c0, c1);
          if (p == 0) mbar_expect_tx(fb, U);
        }
      } else if (warp == 15) {
        const unsigned ep1 = ld_x1(&g_epoch[blockIdx.x * 8]) + 1;
        flag_wait(&g_cntX[helper ? 0 : 32 * j], ep1 * 16u);
        PROF_EV(22);
        mbar_expect_tx(bars + 8 * B_HX, U);
        bulk_load(sb + OFF_XB, g_X + (size_t)(helper ? 128 : kg * 8 + tn) * 8192, U, bars + 8 * B_HX);
        if (!helper) {
          flag_wait(&g_cntT[32 * j], ep1 * 64u);
          PROF_EV(23);
          mbar_expect_tx(bars + 8 * B_TL, U);
          tma3d(sb + OFF_T, &maps.t, bars + 8 * B_TL, 64 * j, 0, 2 * rb);
#pragma unroll 1
          for (int i = 0; i < 3; i++) {
            mbar_wait(bars + 8 * (B_PZ + (i >> 1)), 0);
            flag_wait(&g_cntP[32 * (rb * 8 + j) + i], ep1 * 8u);
            if (i == 2) PROF_EV(26);
            mbar_expect_tx(bars + 8 * (B_HP + i), U);
            bulk_load(sb + i * U, g_part + (size_t)((rb * 8 + j) * 3 + i) * 1024, U, bars + 8 * (B_HP + i));
          }
          g_epoch[blockIdx.x * 8] = ep1;
        }
      } else {
#pragma unroll 1
        for (int q = 4; q < 8; q++) xf_load(q);
        mbar_wait(bars + 8 * (B_FE + 2), 0);
        mbar_expect_tx(bars + 8 * B_E0, U);
        tma2d(sb + OFF_XB, &maps.e, bars + 8 * B_E0, 0, 2 * rb * 128);
        tma2d(sb + OFF_XB + 8192, &maps.e, bars + 8 * B_E0, 0, 2 * rb * 128 + 64);
#pragma unroll 1
        for (int h2 = 0; h2 < 2; h2++) {
          const int s0 = 2 * rb + h2, sg = (s0 & ~6) | ((s0 & 2) << 1) | ((s0 & 4) >> 1);
          mbar_wait(bars + 8 * (B_XS + h2), 0);
#pragma unroll 1
          for (int c = 0; c < 2; c++) {
            asm volatile("cp.async.bulk.tensor.4d.global.shared::cta.bulk_group [%0, {%2, %3, %4, %5}], [%1];" ::"l"(&maps.xs),
                         "r"(sb + OFF_XB + h2 * 8192 + c * 4096), "r"(0), "r"(sg), "r"(0), "r"(16 * j + 8 * c) : "memory");
            if (j == 0)
              asm volatile("cp.async.bulk.global.shared::cta.bulk_group [%0], [%1], 256;" ::"l"(g_X + 128 * 8192 + c * 4096 + sg * 128),
                           "r"(sb + OFF_SP + h2 * 512 + c * 256) : "memory");
            if (SPACE && h2 + c < 2) __nanosleep(SPACE);
          }
        }
        bulk_done_signal(&g_cntX[32 * j]);
        PROF_EV(20);
#pragma unroll 1
        for (int t = 0; t < 8; t++) {
          const int i = t < 3 ? t + 1 : t < 6 ? t - 2 : 0;
          const int col = 64 * (2 * ((q4 + i) & 3) + ((t < 3 || t == 6) ? 1 - rank : rank));
          const uint32_t fb = bars + 8 * (B_FT + (t & 3)), dst = sb + (t & 3) * TB;
          mbar_wait(bars + 8 * (B_ET + (t == 2 ? 3 : t & 3)), t >> 2);
          mbar_expect_tx(fb, TB);
          tma2d(dst, &maps.d224, fb, col, 224 * j);
          if (t < 2) mbar_wait(bars + 8 * (B_ET + t + 1), 0);
          tma2d(dst + 28672, &maps.ft, fb, col, 64 * j);
        }
      }
    }
  }
}

typedef CUresult (*EncodeFn)(CUtensorMap*, CUtensorMapDataType, cuuint32_t, void*, const cuuint64_t*, const cuuint64_t*, const cuuint32_t*,
                             const cuuint32_t*, CUtensorMapInterleave, CUtensorMapSwizzle, CUtensorMapL2promotion, CUtensorMapFloatOOBfill);

static void encode(EncodeFn f, CUtensorMap* m, const void* base, int rank, const cuuint64_t* dims, const cuuint64_t* strides, const cuuint32_t* box,
                   CUtensorMapSwizzle sw) {
  cuuint32_t es[5] = {1, 1, 1, 1, 1};
  f(m, CU_TENSOR_MAP_DATA_TYPE_BFLOAT16, rank, (void*)base, dims, strides, box, es, CU_TENSOR_MAP_INTERLEAVE_NONE, sw,
    CU_TENSOR_MAP_L2_PROMOTION_L2_128B, CU_TENSOR_MAP_FLOAT_OOB_FILL_NONE);
}

extern "C" void kernel_launch(void* const* d_in, const int* in_sizes, int n_in, void* d_out, int out_size) {
  (void)in_sizes; (void)n_in; (void)out_size;
  const __nv_bfloat16* x = (const __nv_bfloat16*)d_in[0];
  const __nv_bfloat16* w_r = (const __nv_bfloat16*)d_in[1];
  const __nv_bfloat16* w_i = (const __nv_bfloat16*)d_in[2];
  const __nv_bfloat16* Wg = (const __nv_bfloat16*)d_in[4];
  const __nv_bfloat16* Wu = (const __nv_bfloat16*)d_in[5];
  const __nv_bfloat16* Wd = (const __nv_bfloat16*)d_in[6];
  const __nv_bfloat16* gw = (const __nv_bfloat16*)d_in[7];

  void* fp = nullptr; cudaDriverEntryPointQueryResult qr;
  cudaGetDriverEntryPoint("cuTensorMapEncodeTiled", &fp, cudaEnableDefault, &qr);
  EncodeFn enc = (EncodeFn)fp;
  void *pFT, *pET, *pX, *pT;
  cudaGetSymbolAddress(&pX, g_X); cudaGetSymbolAddress(&pT, g_T);
  cudaGetSymbolAddress(&pFT, g_FT); cudaGetSymbolAddress(&pET, g_ET);

  Maps mp;
  const CUtensorMapSwizzle S128 = CU_TENSOR_MAP_SWIZZLE_128B, S64 = CU_TENSOR_MAP_SWIZZLE_64B;
  { cuuint64_t d[3] = {512, 64, 32}, s[2] = {32768, 1024}; cuuint32_t b[3] = {64, 64, 2}; encode(enc, &mp.x, x, 3, d, s, b, S128); }
  { cuuint64_t d[2] = {512, 512}, s[1] = {1024}; cuuint32_t b[2] = {64, 64}; encode(enc, &mp.ft, pFT, 2, d, s, b, S128); }
  { cuuint64_t d[4] = {128, 32, 2, 129}, s[3] = {256, 8192, 16384}; cuuint32_t b[4] = {128, 1, 2, 8}; encode(enc, &mp.xs, pX, 4, d, s, b, CU_TENSOR_MAP_SWIZZLE_NONE); }
  { cuuint64_t d[3] = {512, 32, 64}, s[2] = {65536, 1024}; cuuint32_t b[3] = {32, 32, 2}; encode(enc, &mp.ts, pT, 3, d, s, b, S64); }
  { cuuint64_t d[3] = {512, 64, 32}, s[2] = {1024, 65536}; cuuint32_t b[3] = {64, 64, 2}; encode(enc, &mp.t, pT, 3, d, s, b, S128); }
  { cuuint64_t d[2] = {64, 4096}, s[1] = {128}; cuuint32_t b[2] = {64, 64}; encode(enc, &mp.e, pET, 2, d, s, b, S128); }
  { cuuint64_t d[2] = {1792, 512}, s[1] = {3584}; cuuint32_t b[2] = {64, 64}, b2[2] = {32, 128};
    encode(enc, &mp.g64, Wg, 2, d, s, b, S128); encode(enc, &mp.u64, Wu, 2, d, s, b, S128);
    encode(enc, &mp.g32, Wg, 2, d, s, b2, S64); encode(enc, &mp.u32, Wu, 2, d, s, b2, S64); }
  { cuuint64_t d[2] = {512, 1792}, s[1] = {1024}; cuuint32_t b[2] = {64, 224}; encode(enc, &mp.d224, Wd, 2, d, s, b, S128); }
  { cuuint64_t d[4] = {264, 32, 8, 8}, s[3] = {32896, 512, 4112}; cuuint32_t b[4] = {24, 32, 2, 1};
    encode(enc, &mp.wr, w_r, 4, d, s, b, CU_TENSOR_MAP_SWIZZLE_NONE); encode(enc, &mp.wi, w_i, 4, d, s, b, CU_TENSOR_MAP_SWIZZLE_NONE); }

  cudaFuncSetAttribute(fused_kernel, cudaFuncAttributeMaxDynamicSharedMemorySize, SMEM_BYTES);
  fused_kernel<<<NCTA, 512, SMEM_BYTES>>>(mp, w_r, w_i, gw, (__nv_bfloat16*)d_out);
}
```

```cpp
#include <cuda_runtime.h>
#include <cuda_bf16.h>
#include <cuda.h>
#include <stdint.h>

namespace tbl {
constexpr double PI = 3.14159265358979323846264338327950288;
constexpr double sin_s(double x) { double t = x, s = x; for (int n = 1; n < 12; n++) { t *= -x * x / ((2 * n) * (2 * n + 1)); s += t; } return s; }
constexpr double cos_s(double x) { double t = 1, s = 1; for (int n = 1; n < 12; n++) { t *= -x * x / ((2 * n - 1) * (2 * n)); s += t; } return s; }
constexpr double cos2048(int m) {
  m &= 2047; if (m > 1024) m = 2048 - m;
  bool neg = false; if (m > 512) { m = 1024 - m; neg = true; }
  double v = (m <= 256) ? cos_s(2 * PI * m / 2048) : sin_s(2 * PI * (512 - m) / 2048);
  return neg ? -v : v;
}
constexpr uint16_t to_bf16(double v) {
  if (v == 0) return 0;
  uint16_t s = 0; if (v < 0) { s = 0x8000; v = -v; }
  int e = 0; while (v >= 2) { v /= 2; e++; } while (v < 1) { v *= 2; e--; }
  double m = (v - 1) * 128; int mi = (int)m; double fr = m - mi;
  if (fr > 0.5 || (fr == 0.5 && (mi & 1))) mi++;
  if (mi == 128) { mi = 0; e++; }
  return (uint16_t)(s | ((e + 127) << 7) | mi);
}
struct CosT { uint16_t v[2048]; constexpr CosT() : v() { for (int i = 0; i < 2048; i++) v[i] = to_bf16(cos2048(i)); } };
struct alignas(1024) FT {
  uint16_t v[512 * 512];
  constexpr FT() : v() {
    CosT c;
    for (int r = 0; r < 512; r++) {
      int k = (r >> 4) * 8 + (r & 7), e = (r >> 3) & 1;
      int mul = 4 * k, add = e ? 512 : 0;
      if (k == 0 && e == 1) { mul = 1024; add = 0; }
      for (int d = 0; d < 512; d++) v[r * 512 + d] = c.v[(d * mul + add) & 2047];
    }
  }
};
struct alignas(1024) ET {
  uint16_t v[2048 * 128];
  constexpr ET() : v() {
    CosT c;
    for (int s = 0; s < 2048; s++)
      for (int j = 0; j < 64; j++) {
        const int o = (s & 31) * 8192 + (s >> 5) * 64 + j;
        v[o] = c.v[(s * j) & 2047]; v[o + 4096] = c.v[(s * j + 512) & 2047];
      }
  }
};
struct alignas(1024) DT {
  uint16_t v[64 * 64];
  constexpr DT() : v() {
    CosT c;
    for (int r = 0; r < 64; r++)
      for (int n = 0; n < 64; n++) {
        const int sg = r >> 1, s0 = (sg & ~6) | ((sg & 2) << 1) | ((sg & 4) >> 1), e = r & 1, f = n & 1;
        const int m = 64 * s0 * (n >> 1) + (e == f ? 0 : e ? -512 : 512);
        v[r * 64 + (((n >> 3) ^ (r & 7)) << 3) + (n & 7)] = c.v[m & 2047];
      }
  }
};
}

__device__ constexpr tbl::FT g_FT = tbl::FT();
__device__ constexpr tbl::ET g_ET = tbl::ET();
__device__ constexpr tbl::DT g_DT = tbl::DT();

__device__ __align__(1024) uint16_t g_X[129 * 8192];
__device__ __align__(1024) uint16_t g_T[32 * 64 * 512];
__device__ __align__(1024) uint2 g_Ts[32 * 64];
__device__ __align__(1024) uint4 g_part[128 * 3 * 1024];
__device__ __align__(16) float g_gate[16 * 128];
__device__ __align__(16) uint2 g_Wh[2 * 2048];
__device__ unsigned g_epoch[132 * 8];
__device__ unsigned g_cntX[8 * 32], g_cntT[8 * 32], g_cntP[128 * 32], g_cntW[32], g_cntH[32];
#define PROF_EV(i) do {} while (0)
#define PROF_CK(i) do {} while (0)

__device__ __forceinline__ uint32_t smem_u32(const void* p) { return (uint32_t)__cvta_generic_to_shared(p); }
__device__ __forceinline__ void mbar_init(uint32_t bar, uint32_t cnt) { asm volatile("mbarrier.init.shared::cta.b64 [%0], %1;" ::"r"(bar), "r"(cnt)); }
__device__ __forceinline__ void mbar_expect_tx(uint32_t bar, uint32_t bytes) { asm volatile("mbarrier.arrive.expect_tx.shared::cta.b64 _, [%0], %1;" ::"r"(bar), "r"(bytes) : "memory"); }
__device__ __forceinline__ void mbar_arrive(uint32_t bar) { asm volatile("mbarrier.arrive.shared::cta.b64 _, [%0];" ::"r"(bar) : "memory"); }
__device__ __forceinline__ bool elect_one() {
  uint32_t p;
  asm volatile("{\n.reg .pred p;\nelect.sync _|p, 0xffffffff;\nselp.u32 %0, 1, 0, p;\n}" : "=r"(p));
  return p;
}
__device__ __forceinline__ void mbar_arrive_if(bool p, uint32_t bar) {
  asm volatile("{\n.reg .pred p;\nsetp.ne.b32 p, %1, 0;\n@p mbarrier.arrive.shared::cta.b64 _, [%0];\n}" ::"r"(bar), "r"((int)p) : "memory");
}
__device__ __forceinline__ void hint_add_if(bool p, unsigned* a) {
  asm volatile("{\n.reg .pred p;\nsetp.ne.b32 p, %1, 0;\n@p red.relaxed.gpu.global.add.u32 [%0], 1;\n}" ::"l"(a), "r"((int)p) : "memory");
}
__device__ __forceinline__ bool mbar_try(uint32_t bar, uint32_t parity) {
  uint32_t ok;
  asm volatile("{\n.reg .pred p;\nmbarrier.test_wait.parity.shared::cta.b64 p, [%1], %2;\nselp.u32 %0, 1, 0, p;\n}" : "=r"(ok) : "r"(bar), "r"(parity) : "memory");
  return ok;
}
__device__ __forceinline__ void mbar_wait(uint32_t bar, uint32_t parity) {
  asm volatile(
      "{\n.reg .pred p;\n.reg .u32 n;\nmov.u32 n, 0;\n"
      "W_LOOP:\nmbarrier.try_wait.parity.shared::cta.b64 p, [%0], %1;\n@p bra W_DONE;\n"
      "add.u32 n, n, 1;\nsetp.lt.u32 p, n, 0x40000;\n@p bra W_LOOP;\ntrap;\nW_DONE:\n}" ::"r"(bar), "r"(parity) : "memory");
}
__device__ __forceinline__ void bulk_load(uint32_t dst, const void* src, uint32_t bytes, uint32_t bar) {
  asm volatile("cp.async.bulk.shared::cluster.global.mbarrier::complete_tx::bytes [%0], [%1], %2, [%3];" ::"r"(dst), "l"(src), "r"(bytes), "r"(bar) : "memory");
}
__device__ __forceinline__ void cp16(uint32_t dst, const void* src) { asm volatile("cp.async.cg.shared.global [%0], [%1], 16;" ::"r"(dst), "l"(src) : "memory"); }
__device__ __forceinline__ void spin_guard(uint32_t t0) { if ((uint32_t)clock() - t0 > (1u << 30)) __trap(); }
__device__ __forceinline__ float tagf(float v, uint32_t tag) { return __uint_as_float((__float_as_uint(v) & ~1u) | tag); }
__device__ __forceinline__ float untag(float v) { return __uint_as_float(__float_as_uint(v) & ~1u); }
__device__ __forceinline__ void st_x2(float2* p, float a, float b) { asm volatile("st.relaxed.gpu.global.v2.f32 [%0], {%1,%2};" ::"l"(p), "f"(a), "f"(b) : "memory"); }
__device__ __forceinline__ float2 ld_x2(const float2* p) { float2 v; asm volatile("ld.relaxed.gpu.global.v2.f32 {%0,%1}, [%2];" : "=f"(v.x), "=f"(v.y) : "l"(p) : "memory"); return v; }
__device__ __forceinline__ void st_u2(uint2* p, uint32_t a, uint32_t b) { asm volatile("st.relaxed.gpu.global.v2.u32 [%0], {%1,%2};" ::"l"(p), "r"(a), "r"(b) : "memory"); }
__device__ __forceinline__ void prefetch2d(const CUtensorMap* m, int c0, int c1) { asm volatile("cp.async.bulk.prefetch.tensor.2d.L2.global [%0, {%1, %2}];" ::"l"(m), "r"(c0), "r"(c1) : "memory"); }
__device__ __forceinline__ void prefetch1d(const void* p, uint32_t bytes) { asm volatile("cp.async.bulk.prefetch.L2.global [%0], %1;" ::"l"(p), "r"(bytes) : "memory"); }
__device__ __forceinline__ uint32_t ld_x1(const void* p) { uint32_t v; asm volatile("ld.relaxed.gpu.global.u32 %0, [%1];" : "=r"(v) : "l"(p) : "memory"); return v; }
__device__ __forceinline__ uint4 ld_x4(const void* p) { uint4 v; asm volatile("ld.relaxed.gpu.global.v4.u32 {%0,%1,%2,%3}, [%4];" : "=r"(v.x), "=r"(v.y), "=r"(v.z), "=r"(v.w) : "l"(p) : "memory"); return v; }
__device__ __forceinline__ void st_x4(void* p, uint32_t a, uint32_t b, uint32_t c, uint32_t d) { asm volatile("st.relaxed.gpu.global.v4.u32 [%0], {%1,%2,%3,%4};" ::"l"(p), "r"(a), "r"(b), "r"(c), "r"(d) : "memory"); }
__device__ __forceinline__ uint32_t mapa(uint32_t a, uint32_t cta) { uint32_t r; asm volatile("mapa.shared::cluster.u32 %0, %1, %2;" : "=r"(r) : "r"(a), "r"(cta)); return r; }
__device__ __forceinline__ void stsm4t(uint32_t a, uint32_t r0, uint32_t r1, uint32_t r2, uint32_t r3) {
  asm volatile("stmatrix.sync.aligned.m8n8.x4.trans.shared.b16 [%0], {%1,%2,%3,%4};" ::"r"(a), "r"(r0), "r"(r1), "r"(r2), "r"(r3) : "memory");
}
__device__ __forceinline__ void hint_add(unsigned* p) { asm volatile("red.relaxed.gpu.global.add.u32 [%0], 1;" ::"l"(p) : "memory"); }
__device__ __forceinline__ void hint_wait(const unsigned* p, unsigned target) {
  const uint32_t t0 = (uint32_t)clock();
  while ((int)(ld_x1(p) - target) < 0) spin_guard(t0);
}
__device__ __forceinline__ void bulk_done_signal(unsigned* p) {
  asm volatile("cp.async.bulk.commit_group;\ncp.async.bulk.wait_group 0;\nfence.proxy.async.global;" ::: "memory");
  hint_add(p);
}
__device__ __forceinline__ void flag_wait(const unsigned* p, unsigned target) {
  hint_wait(p, target);
  asm volatile("fence.proxy.async.global;" ::: "memory");
}
__device__ __forceinline__ void tma2d(uint32_t dst, const CUtensorMap* m, uint32_t bar, int c0, int c1) {
  asm volatile("cp.async.bulk.tensor.2d.shared::cluster.global.mbarrier::complete_tx::bytes [%0], [%1, {%3, %4}], [%2];" ::"r"(dst), "l"(m), "r"(bar), "r"(c0), "r"(c1) : "memory");
}
__device__ __forceinline__ void tma3d(uint32_t dst, const CUtensorMap* m, uint32_t bar, int c0, int c1, int c2) {
  asm volatile("cp.async.bulk.tensor.3d.shared::cluster.global.mbarrier::complete_tx::bytes [%0], [%1, {%3, %4, %5}], [%2];" ::"r"(dst), "l"(m), "r"(bar), "r"(c0), "r"(c1), "r"(c2) : "memory");
}
__device__ __forceinline__ void tma4d(uint32_t dst, const CUtensorMap* m, uint32_t bar, int c0, int c1, int c2, int c3) {
  asm volatile("cp.async.bulk.tensor.4d.shared::cluster.global.mbarrier::complete_tx::bytes [%0], [%1, {%3, %4, %5, %6}], [%2];" ::"r"(dst), "l"(m), "r"(bar), "r"(c0), "r"(c1), "r"(c2), "r"(c3) : "memory");
}
__device__ __forceinline__ void wg_fence() { asm volatile("wgmma.fence.sync.aligned;" ::: "memory"); }
__device__ __forceinline__ void wg_commit() { asm volatile("wgmma.commit_group.sync.aligned;" ::: "memory"); }
template <int N> __device__ __forceinline__ void wg_wait() { asm volatile("wgmma.wait_group.sync.aligned %0;" ::"n"(N) : "memory"); }
template <int O, int N, int NN> __device__ __forceinline__ void fence_regs(float (&d)[NN]) {
#pragma unroll
  for (int i = 0; i < N; i++) asm volatile("" : "+f"(d[O + i])::"memory");
}
__device__ __forceinline__ uint32_t pack_bf16(float lo, float hi) {
  uint32_t r; asm("cvt.rn.bf16x2.f32 %0, %1, %2;" : "=r"(r) : "f"(hi), "f"(lo)); return r;
}
__device__ __forceinline__ uint32_t pack_pin(float lo, float hi) {
  uint32_t r; asm volatile("cvt.rn.bf16x2.f32 %0, %1, %2;" : "=r"(r) : "f"(hi), "f"(lo) : "memory"); return r;
}
__device__ __forceinline__ float bf_lo(uint32_t u) { return __uint_as_float(u << 16); }
__device__ __forceinline__ float bf_hi(uint32_t u) { return __uint_as_float(u & 0xffff0000u); }

__device__ __forceinline__ uint64_t d128(uint32_t lo) { uint64_t d; asm("mov.b64 %0, {%1, 0x40000040};" : "=l"(d) : "r"(lo)); return d; }
__device__ __forceinline__ uint64_t d64(uint32_t lo) { uint64_t d; asm("mov.b64 %0, {%1, 0x80000020};" : "=l"(d) : "r"(lo)); return d; }
template<int O,int TB,int ACC,int NN> __device__ __forceinline__ void mma_ss64(float (&d)[NN], uint64_t da, uint64_t db, int sd = 0){
  if constexpr (ACC == 1) asm volatile("wgmma.mma_async.sync.aligned.m64n64k16.f32.bf16.bf16 {%0,%1,%2,%3,%4,%5,%6,%7,%8,%9,%10,%11,%12,%13,%14,%15,%16,%17,%18,%19,%20,%21,%22,%23,%24,%25,%26,%27,%28,%29,%30,%31}, %32, %33, 1, 1, 1, %35, %34;"
   : "+f"(d[O+0]), "+f"(d[O+1]), "+f"(d[O+2]), "+f"(d[O+3]), "+f"(d[O+4]), "+f"(d[O+5]), "+f"(d[O+6]), "+f"(d[O+7]), "+f"(d[O+8]), "+f"(d[O+9]), "+f"(d[O+10]), "+f"(d[O+11]), "+f"(d[O+12]), "+f"(d[O+13]), "+f"(d[O+14]), "+f"(d[O+15]), "+f"(d[O+16]), "+f"(d[O+17]), "+f"(d[O+18]), "+f"(d[O+19]), "+f"(d[O+20]), "+f"(d[O+21]), "+f"(d[O+22]), "+f"(d[O+23]), "+f"(d[O+24]), "+f"(d[O+25]), "+f"(d[O+26]), "+f"(d[O+27]), "+f"(d[O+28]), "+f"(d[O+29]), "+f"(d[O+30]), "+f"(d[O+31])
   : "l"(da), "l"(db), "n"(TB & 1), "n"(TB >> 1));
  else if constexpr (ACC == 0) asm volatile("wgmma.mma_async.sync.aligned.m64n64k16.f32.bf16.bf16 {%0,%1,%2,%3,%4,%5,%6,%7,%8,%9,%10,%11,%12,%13,%14,%15,%16,%17,%18,%19,%20,%21,%22,%23,%24,%25,%26,%27,%28,%29,%30,%31}, %32, %33, 0, 1, 1, %35, %34;"
   : "=f"(d[O+0]), "=f"(d[O+1]), "=f"(d[O+2]), "=f"(d[O+3]), "=f"(d[O+4]), "=f"(d[O+5]), "=f"(d[O+6]), "=f"(d[O+7]), "=f"(d[O+8]), "=f"(d[O+9]), "=f"(d[O+10]), "=f"(d[O+11]), "=f"(d[O+12]), "=f"(d[O+13]), "=f"(d[O+14]), "=f"(d[O+15]), "=f"(d[O+16]), "=f"(d[O+17]), "=f"(d[O+18]), "=f"(d[O+19]), "=f"(d[O+20]), "=f"(d[O+21]), "=f"(d[O+22]), "=f"(d[O+23]), "=f"(d[O+24]), "=f"(d[O+25]), "=f"(d[O+26]), "=f"(d[O+27]), "=f"(d[O+28]), "=f"(d[O+29]), "=f"(d[O+30]), "=f"(d[O+31])
   : "l"(da), "l"(db), "n"(TB & 1), "n"(TB >> 1));
  else asm volatile("{\n.reg .pred p;\nsetp.ne.b32 p, %36, 0;\nwgmma.mma_async.sync.aligned.m64n64k16.f32.bf16.bf16 {%0,%1,%2,%3,%4,%5,%6,%7,%8,%9,%10,%11,%12,%13,%14,%15,%16,%17,%18,%19,%20,%21,%22,%23,%24,%25,%26,%27,%28,%29,%30,%31}, %32, %33, p, 1, 1, %35, %34;\n}"
   : "+f"(d[O+0]), "+f"(d[O+1]), "+f"(d[O+2]), "+f"(d[O+3]), "+f"(d[O+4]), "+f"(d[O+5]), "+f"(d[O+6]), "+f"(d[O+7]), "+f"(d[O+8]), "+f"(d[O+9]), "+f"(d[O+10]), "+f"(d[O+11]), "+f"(d[O+12]), "+f"(d[O+13]), "+f"(d[O+14]), "+f"(d[O+15]), "+f"(d[O+16]), "+f"(d[O+17]), "+f"(d[O+18]), "+f"(d[O+19]), "+f"(d[O+20]), "+f"(d[O+21]), "+f"(d[O+22]), "+f"(d[O+23]), "+f"(d[O+24]), "+f"(d[O+25]), "+f"(d[O+26]), "+f"(d[O+27]), "+f"(d[O+28]), "+f"(d[O+29]), "+f"(d[O+30]), "+f"(d[O+31])
   : "l"(da), "l"(db), "n"(TB & 1), "n"(TB >> 1), "r"(sd));
}
template<int O,int TB,int ACC,int NN> __device__ __forceinline__ void mma_rs64(float (&d)[NN], uint32_t a0, uint32_t a1, uint32_t a2, uint32_t a3, uint64_t db, int sd = 0){
  if constexpr (ACC == 1) asm volatile("wgmma.mma_async.sync.aligned.m64n64k16.f32.bf16.bf16 {%0,%1,%2,%3,%4,%5,%6,%7,%8,%9,%10,%11,%12,%13,%14,%15,%16,%17,%18,%19,%20,%21,%22,%23,%24,%25,%26,%27,%28,%29,%30,%31}, {%32,%33,%34,%35}, %36, 1, 1, 1, %37;"
   : "+f"(d[O+0]), "+f"(d[O+1]), "+f"(d[O+2]), "+f"(d[O+3]), "+f"(d[O+4]), "+f"(d[O+5]), "+f"(d[O+6]), "+f"(d[O+7]), "+f"(d[O+8]), "+f"(d[O+9]), "+f"(d[O+10]), "+f"(d[O+11]), "+f"(d[O+12]), "+f"(d[O+13]), "+f"(d[O+14]), "+f"(d[O+15]), "+f"(d[O+16]), "+f"(d[O+17]), "+f"(d[O+18]), "+f"(d[O+19]), "+f"(d[O+20]), "+f"(d[O+21]), "+f"(d[O+22]), "+f"(d[O+23]), "+f"(d[O+24]), "+f"(d[O+25]), "+f"(d[O+26]), "+f"(d[O+27]), "+f"(d[O+28]), "+f"(d[O+29]), "+f"(d[O+30]), "+f"(d[O+31])
   : "r"(a0), "r"(a1), "r"(a2), "r"(a3), "l"(db), "n"(TB));
  else if constexpr (ACC == 0) asm volatile("wgmma.mma_async.sync.aligned.m64n64k16.f32.bf16.bf16 {%0,%1,%2,%3,%4,%5,%6,%7,%8,%9,%10,%11,%12,%13,%14,%15,%16,%17,%18,%19,%20,%21,%22,%23,%24,%25,%26,%27,%28,%29,%30,%31}, {%32,%33,%34,%35}, %36, 0, 1, 1, %37;"
   : "=f"(d[O+0]), "=f"(d[O+1]), "=f"(d[O+2]), "=f"(d[O+3]), "=f"(d[O+4]), "=f"(d[O+5]), "=f"(d[O+6]), "=f"(d[O+7]), "=f"(d[O+8]), "=f"(d[O+9]), "=f"(d[O+10]), "=f"(d[O+11]), "=f"(d[O+12]), "=f"(d[O+13]), "=f"(d[O+14]), "=f"(d[O+15]), "=f"(d[O+16]), "=f"(d[O+17]), "=f"(d[O+18]), "=f"(d[O+19]), "=f"(d[O+20]), "=f"(d[O+21]), "=f"(d[O+22]), "=f"(d[O+23]), "=f"(d[O+24]), "=f"(d[O+25]), "=f"(d[O+26]), "=f"(d[O+27]), "=f"(d[O+28]), "=f"(d[O+29]), "=f"(d[O+30]), "=f"(d[O+31])
   : "r"(a0), "r"(a1), "r"(a2), "r"(a3), "l"(db), "n"(TB));
  else asm volatile("{\n.reg .pred p;\nsetp.ne.b32 p, %38, 0;\nwgmma.mma_async.sync.aligned.m64n64k16.f32.bf16.bf16 {%0,%1,%2,%3,%4,%5,%6,%7,%8,%9,%10,%11,%12,%13,%14,%15,%16,%17,%18,%19,%20,%21,%22,%23,%24,%25,%26,%27,%28,%29,%30,%31}, {%32,%33,%34,%35}, %36, p, 1, 1, %37;\n}"
   : "+f"(d[O+0]), "+f"(d[O+1]), "+f"(d[O+2]), "+f"(d[O+3]), "+f"(d[O+4]), "+f"(d[O+5]), "+f"(d[O+6]), "+f"(d[O+7]), "+f"(d[O+8]), "+f"(d[O+9]), "+f"(d[O+10]), "+f"(d[O+11]), "+f"(d[O+12]), "+f"(d[O+13]), "+f"(d[O+14]), "+f"(d[O+15]), "+f"(d[O+16]), "+f"(d[O+17]), "+f"(d[O+18]), "+f"(d[O+19]), "+f"(d[O+20]), "+f"(d[O+21]), "+f"(d[O+22]), "+f"(d[O+23]), "+f"(d[O+24]), "+f"(d[O+25]), "+f"(d[O+26]), "+f"(d[O+27]), "+f"(d[O+28]), "+f"(d[O+29]), "+f"(d[O+30]), "+f"(d[O+31])
   : "r"(a0), "r"(a1), "r"(a2), "r"(a3), "l"(db), "n"(TB), "r"(sd));
}
template<int O,int TB,int ACC,int NN> __device__ __forceinline__ void mma_ss128(float (&d)[NN], uint64_t da, uint64_t db, int sd = 0){
  if constexpr (ACC == 1) asm volatile("wgmma.mma_async.sync.aligned.m64n128k16.f32.bf16.bf16 {%0,%1,%2,%3,%4,%5,%6,%7,%8,%9,%10,%11,%12,%13,%14,%15,%16,%17,%18,%19,%20,%21,%22,%23,%24,%25,%26,%27,%28,%29,%30,%31,%32,%33,%34,%35,%36,%37,%38,%39,%40,%41,%42,%43,%44,%45,%46,%47,%48,%49,%50,%51,%52,%53,%54,%55,%56,%57,%58,%59,%60,%61,%62,%63}, %64, %65, 1, 1, 1, %67, %66;"
   : "+f"(d[O+0]), "+f"(d[O+1]), "+f"(d[O+2]), "+f"(d[O+3]), "+f"(d[O+4]), "+f"(d[O+5]), "+f"(d[O+6]), "+f"(d[O+7]), "+f"(d[O+8]), "+f"(d[O+9]), "+f"(d[O+10]), "+f"(d[O+11]), "+f"(d[O+12]), "+f"(d[O+13]), "+f"(d[O+14]), "+f"(d[O+15]), "+f"(d[O+16]), "+f"(d[O+17]), "+f"(d[O+18]), "+f"(d[O+19]), "+f"(d[O+20]), "+f"(d[O+21]), "+f"(d[O+22]), "+f"(d[O+23]), "+f"(d[O+24]), "+f"(d[O+25]), "+f"(d[O+26]), "+f"(d[O+27]), "+f"(d[O+28]), "+f"(d[O+29]), "+f"(d[O+30]), "+f"(d[O+31]), "+f"(d[O+32]), "+f"(d[O+33]), "+f"(d[O+34]), "+f"(d[O+35]), "+f"(d[O+36]), "+f"(d[O+37]), "+f"(d[O+38]), "+f"(d[O+39]), "+f"(d[O+40]), "+f"(d[O+41]), "+f"(d[O+42]), "+f"(d[O+43]), "+f"(d[O+44]), "+f"(d[O+45]), "+f"(d[O+46]), "+f"(d[O+47]), "+f"(d[O+48]), "+f"(d[O+49]), "+f"(d[O+50]), "+f"(d[O+51]), "+f"(d[O+52]), "+f"(d[O+53]), "+f"(d[O+54]), "+f"(d[O+55]), "+f"(d[O+56]), "+f"(d[O+57]), "+f"(d[O+58]), "+f"(d[O+59]), "+f"(d[O+60]), "+f"(d[O+61]), "+f"(d[O+62]), "+f"(d[O+63])
   : "l"(da), "l"(db), "n"(TB & 1), "n"(TB >> 1));
  else if constexpr (ACC == 0) asm volatile("wgmma.mma_async.sync.aligned.m64n128k16.f32.bf16.bf16 {%0,%1,%2,%3,%4,%5,%6,%7,%8,%9,%10,%11,%12,%13,%14,%15,%16,%17,%18,%19,%20,%21,%22,%23,%24,%25,%26,%27,%28,%29,%30,%31,%32,%33,%34,%35,%36,%37,%38,%39,%40,%41,%42,%43,%44,%45,%46,%47,%48,%49,%50,%51,%52,%53,%54,%55,%56,%57,%58,%59,%60,%61,%62,%63}, %64, %65, 0, 1, 1, %67, %66;"
   : "=f"(d[O+0]), "=f"(d[O+1]), "=f"(d[O+2]), "=f"(d[O+3]), "=f"(d[O+4]), "=f"(d[O+5]), "=f"(d[O+6]), "=f"(d[O+7]), "=f"(d[O+8]), "=f"(d[O+9]), "=f"(d[O+10]), "=f"(d[O+11]), "=f"(d[O+12]), "=f"(d[O+13]), "=f"(d[O+14]), "=f"(d[O+15]), "=f"(d[O+16]), "=f"(d[O+17]), "=f"(d[O+18]), "=f"(d[O+19]), "=f"(d[O+20]), "=f"(d[O+21]), "=f"(d[O+22]), "=f"(d[O+23]), "=f"(d[O+24]), "=f"(d[O+25]), "=f"(d[O+26]), "=f"(d[O+27]), "=f"(d[O+28]), "=f"(d[O+29]), "=f"(d[O+30]), "=f"(d[O+31]), "=f"(d[O+32]), "=f"(d[O+33]), "=f"(d[O+34]), "=f"(d[O+35]), "=f"(d[O+36]), "=f"(d[O+37]), "=f"(d[O+38]), "=f"(d[O+39]), "=f"(d[O+40]), "=f"(d[O+41]), "=f"(d[O+42]), "=f"(d[O+43]), "=f"(d[O+44]), "=f"(d[O+45]), "=f"(d[O+46]), "=f"(d[O+47]), "=f"(d[O+48]), "=f"(d[O+49]), "=f"(d[O+50]), "=f"(d[O+51]), "=f"(d[O+52]), "=f"(d[O+53]), "=f"(d[O+54]), "=f"(d[O+55]), "=f"(d[O+56]), "=f"(d[O+57]), "=f"(d[O+58]), "=f"(d[O+59]), "=f"(d[O+60]), "=f"(d[O+61]), "=f"(d[O+62]), "=f"(d[O+63])
   : "l"(da), "l"(db), "n"(TB & 1), "n"(TB >> 1));
  else asm volatile("{\n.reg .pred p;\nsetp.ne.b32 p, %68, 0;\nwgmma.mma_async.sync.aligned.m64n128k16.f32.bf16.bf16 {%0,%1,%2,%3,%4,%5,%6,%7,%8,%9,%10,%11,%12,%13,%14,%15,%16,%17,%18,%19,%20,%21,%22,%23,%24,%25,%26,%27,%28,%29,%30,%31,%32,%33,%34,%35,%36,%37,%38,%39,%40,%41,%42,%43,%44,%45,%46,%47,%48,%49,%50,%51,%52,%53,%54,%55,%56,%57,%58,%59,%60,%61,%62,%63}, %64, %65, p, 1, 1, %67, %66;\n}"
   : "+f"(d[O+0]), "+f"(d[O+1]), "+f"(d[O+2]), "+f"(d[O+3]), "+f"(d[O+4]), "+f"(d[O+5]), "+f"(d[O+6]), "+f"(d[O+7]), "+f"(d[O+8]), "+f"(d[O+9]), "+f"(d[O+10]), "+f"(d[O+11]), "+f"(d[O+12]), "+f"(d[O+13]), "+f"(d[O+14]), "+f"(d[O+15]), "+f"(d[O+16]), "+f"(d[O+17]), "+f"(d[O+18]), "+f"(d[O+19]), "+f"(d[O+20]), "+f"(d[O+21]), "+f"(d[O+22]), "+f"(d[O+23]), "+f"(d[O+24]), "+f"(d[O+25]), "+f"(d[O+26]), "+f"(d[O+27]), "+f"(d[O+28]), "+f"(d[O+29]), "+f"(d[O+30]), "+f"(d[O+31]), "+f"(d[O+32]), "+f"(d[O+33]), "+f"(d[O+34]), "+f"(d[O+35]), "+f"(d[O+36]), "+f"(d[O+37]), "+f"(d[O+38]), "+f"(d[O+39]), "+f"(d[O+40]), "+f"(d[O+41]), "+f"(d[O+42]), "+f"(d[O+43]), "+f"(d[O+44]), "+f"(d[O+45]), "+f"(d[O+46]), "+f"(d[O+47]), "+f"(d[O+48]), "+f"(d[O+49]), "+f"(d[O+50]), "+f"(d[O+51]), "+f"(d[O+52]), "+f"(d[O+53]), "+f"(d[O+54]), "+f"(d[O+55]), "+f"(d[O+56]), "+f"(d[O+57]), "+f"(d[O+58]), "+f"(d[O+59]), "+f"(d[O+60]), "+f"(d[O+61]), "+f"(d[O+62]), "+f"(d[O+63])
   : "l"(da), "l"(db), "n"(TB & 1), "n"(TB >> 1), "r"(sd));
}
template<int O,int TB,int ACC,int NN> __device__ __forceinline__ void mma_rs128(float (&d)[NN], uint32_t a0, uint32_t a1, uint32_t a2, uint32_t a3, uint64_t db, int sd = 0){
  if constexpr (ACC == 1) asm volatile("wgmma.mma_async.sync.aligned.m64n128k16.f32.bf16.bf16 {%0,%1,%2,%3,%4,%5,%6,%7,%8,%9,%10,%11,%12,%13,%14,%15,%16,%17,%18,%19,%20,%21,%22,%23,%24,%25,%26,%27,%28,%29,%30,%31,%32,%33,%34,%35,%36,%37,%38,%39,%40,%41,%42,%43,%44,%45,%46,%47,%48,%49,%50,%51,%52,%53,%54,%55,%56,%57,%58,%59,%60,%61,%62,%63}, {%64,%65,%66,%67}, %68, 1, 1, 1, %69;"
   : "+f"(d[O+0]), "+f"(d[O+1]), "+f"(d[O+2]), "+f"(d[O+3]), "+f"(d[O+4]), "+f"(d[O+5]), "+f"(d[O+6]), "+f"(d[O+7]), "+f"(d[O+8]), "+f"(d[O+9]), "+f"(d[O+10]), "+f"(d[O+11]), "+f"(d[O+12]), "+f"(d[O+13]), "+f"(d[O+14]), "+f"(d[O+15]), "+f"(d[O+16]), "+f"(d[O+17]), "+f"(d[O+18]), "+f"(d[O+19]), "+f"(d[O+20]), "+f"(d[O+21]), "+f"(d[O+22]), "+f"(d[O+23]), "+f"(d[O+24]), "+f"(d[O+25]), "+f"(d[O+26]), "+f"(d[O+27]), "+f"(d[O+28]), "+f"(d[O+29]), "+f"(d[O+30]), "+f"(d[O+31]), "+f"(d[O+32]), "+f"(d[O+33]), "+f"(d[O+34]), "+f"(d[O+35]), "+f"(d[O+36]), "+f"(d[O+37]), "+f"(d[O+38]), "+f"(d[O+39]), "+f"(d[O+40]), "+f"(d[O+41]), "+f"(d[O+42]), "+f"(d[O+43]), "+f"(d[O+44]), "+f"(d[O+45]), "+f"(d[O+46]), "+f"(d[O+47]), "+f"(d[O+48]), "+f"(d[O+49]), "+f"(d[O+50]), "+f"(d[O+51]), "+f"(d[O+52]), "+f"(d[O+53]), "+f"(d[O+54]), "+f"(d[O+55]), "+f"(d[O+56]), "+f"(d[O+57]), "+f"(d[O+58]), "+f"(d[O+59]), "+f"(d[O+60]), "+f"(d[O+61]), "+f"(d[O+62]), "+f"(d[O+63])
   : "r"(a0), "r"(a1), "r"(a2), "r"(a3), "l"(db), "n"(TB));
  else if constexpr (ACC == 0) asm volatile("wgmma.mma_async.sync.aligned.m64n128k16.f32.bf16.bf16 {%0,%1,%2,%3,%4,%5,%6,%7,%8,%9,%10,%11,%12,%13,%14,%15,%16,%17,%18,%19,%20,%21,%22,%23,%24,%25,%26,%27,%28,%29,%30,%31,%32,%33,%34,%35,%36,%37,%38,%39,%40,%41,%42,%43,%44,%45,%46,%47,%48,%49,%50,%51,%52,%53,%54,%55,%56,%57,%58,%59,%60,%61,%62,%63}, {%64,%65,%66,%67}, %68, 0, 1, 1, %69;"
   : "=f"(d[O+0]), "=f"(d[O+1]), "=f"(d[O+2]), "=f"(d[O+3]), "=f"(d[O+4]), "=f"(d[O+5]), "=f"(d[O+6]), "=f"(d[O+7]), "=f"(d[O+8]), "=f"(d[O+9]), "=f"(d[O+10]), "=f"(d[O+11]), "=f"(d[O+12]), "=f"(d[O+13]), "=f"(d[O+14]), "=f"(d[O+15]), "=f"(d[O+16]), "=f"(d[O+17]), "=f"(d[O+18]), "=f"(d[O+19]), "=f"(d[O+20]), "=f"(d[O+21]), "=f"(d[O+22]), "=f"(d[O+23]), "=f"(d[O+24]), "=f"(d[O+25]), "=f"(d[O+26]), "=f"(d[O+27]), "=f"(d[O+28]), "=f"(d[O+29]), "=f"(d[O+30]), "=f"(d[O+31]), "=f"(d[O+32]), "=f"(d[O+33]), "=f"(d[O+34]), "=f"(d[O+35]), "=f"(d[O+36]), "=f"(d[O+37]), "=f"(d[O+38]), "=f"(d[O+39]), "=f"(d[O+40]), "=f"(d[O+41]), "=f"(d[O+42]), "=f"(d[O+43]), "=f"(d[O+44]), "=f"(d[O+45]), "=f"(d[O+46]), "=f"(d[O+47]), "=f"(d[O+48]), "=f"(d[O+49]), "=f"(d[O+50]), "=f"(d[O+51]), "=f"(d[O+52]), "=f"(d[O+53]), "=f"(d[O+54]), "=f"(d[O+55]), "=f"(d[O+56]), "=f"(d[O+57]), "=f"(d[O+58]), "=f"(d[O+59]), "=f"(d[O+60]), "=f"(d[O+61]), "=f"(d[O+62]), "=f"(d[O+63])
   : "r"(a0), "r"(a1), "r"(a2), "r"(a3), "l"(db), "n"(TB));
  else asm volatile("{\n.reg .pred p;\nsetp.ne.b32 p, %70, 0;\nwgmma.mma_async.sync.aligned.m64n128k16.f32.bf16.bf16 {%0,%1,%2,%3,%4,%5,%6,%7,%8,%9,%10,%11,%12,%13,%14,%15,%16,%17,%18,%19,%20,%21,%22,%23,%24,%25,%26,%27,%28,%29,%30,%31,%32,%33,%34,%35,%36,%37,%38,%39,%40,%41,%42,%43,%44,%45,%46,%47,%48,%49,%50,%51,%52,%53,%54,%55,%56,%57,%58,%59,%60,%61,%62,%63}, {%64,%65,%66,%67}, %68, p, 1, 1, %69;\n}"
   : "+f"(d[O+0]), "+f"(d[O+1]), "+f"(d[O+2]), "+f"(d[O+3]), "+f"(d[O+4]), "+f"(d[O+5]), "+f"(d[O+6]), "+f"(d[O+7]), "+f"(d[O+8]), "+f"(d[O+9]), "+f"(d[O+10]), "+f"(d[O+11]), "+f"(d[O+12]), "+f"(d[O+13]), "+f"(d[O+14]), "+f"(d[O+15]), "+f"(d[O+16]), "+f"(d[O+17]), "+f"(d[O+18]), "+f"(d[O+19]), "+f"(d[O+20]), "+f"(d[O+21]), "+f"(d[O+22]), "+f"(d[O+23]), "+f"(d[O+24]), "+f"(d[O+25]), "+f"(d[O+26]), "+f"(d[O+27]), "+f"(d[O+28]), "+f"(d[O+29]), "+f"(d[O+30]), "+f"(d[O+31]), "+f"(d[O+32]), "+f"(d[O+33]), "+f"(d[O+34]), "+f"(d[O+35]), "+f"(d[O+36]), "+f"(d[O+37]), "+f"(d[O+38]), "+f"(d[O+39]), "+f"(d[O+40]), "+f"(d[O+41]), "+f"(d[O+42]), "+f"(d[O+43]), "+f"(d[O+44]), "+f"(d[O+45]), "+f"(d[O+46]), "+f"(d[O+47]), "+f"(d[O+48]), "+f"(d[O+49]), "+f"(d[O+50]), "+f"(d[O+51]), "+f"(d[O+52]), "+f"(d[O+53]), "+f"(d[O+54]), "+f"(d[O+55]), "+f"(d[O+56]), "+f"(d[O+57]), "+f"(d[O+58]), "+f"(d[O+59]), "+f"(d[O+60]), "+f"(d[O+61]), "+f"(d[O+62]), "+f"(d[O+63])
   : "r"(a0), "r"(a1), "r"(a2), "r"(a3), "l"(db), "n"(TB), "r"(sd));
}

#define NEARLY 0
#define XAHEAD 3
#define HEADN 6
#define WBATCH 1
#define SPACE 0
#define WPF 1
#define WAFTER 7
#define WPACE 0
#define GATE_AT 4
#define TPACE 40
#define PFMODE 0
#define MAPMODE 0
template <int V> struct IC { static constexpr int value = V; };
struct Maps { CUtensorMap x, ft, g64, u64, e, wr, wi, xs, ts, t, g32, u32, d224; };

constexpr int NCTA = 130;
constexpr int U = 16384;
constexpr int TB = 36864;
constexpr int OFF_RING = 8 * U, OFF_Z = 9 * U, OFF_XB = 12 * U, OFF_T = 13 * U, OFF_D = OFF_T;
constexpr int OFF_BAR = 14 * U, OFF_SP = OFF_BAR + 512, OFF_G = OFF_SP + 1024 + 128;
constexpr int SMEM_BYTES = OFF_G + 512;
constexpr int B_FX = 0, B_FA = 8, B_FT = 12, B_Z = 16, B_W = 20, B_HX = 21, B_TL = 22, B_HP = 23, B_WR = 26, B_E0 = 30;
constexpr int B_EA = 31, B_ET = 35, B_PZ = 39, B_RDY = 41, B_FE = 42;
constexpr int B_T = 46, B_XS = 47, B_G = 49, NBAR = 50;
__host__ __device__ constexpr int rslot(int n) { return n & 3; }
__host__ __device__ constexpr int rpar(int n) { return (n >> 2) & 1; }

__global__ void __cluster_dims__(2, 1, 1) __launch_bounds__(512, 1)
fused_kernel(const __grid_constant__ Maps maps, const __nv_bfloat16* __restrict__ w_r,
             const __nv_bfloat16* __restrict__ w_i, const __nv_bfloat16* __restrict__ gate_w, __nv_bfloat16* __restrict__ out) {
  extern __shared__ __align__(1024) uint8_t smem[];
  const uint32_t sb = smem_u32(smem);
  const uint32_t bars = sb + OFF_BAR;
  const int tid = threadIdx.x, lane = tid & 31;
  const int warp = __shfl_sync(0xffffffffu, tid >> 5, 0);
  const bool helper = blockIdx.x >= 128;
  const int cl = (blockIdx.x >> 1) & 63, rank = blockIdx.x & 1;
  const int q4 = cl & 3, rb = cl >> 2;
  const int j = 2 * q4 + rank;
  const int f_full = 448 * q4 + (rank ? 256 : 0);
  const int f_half = 448 * q4 + (rank ? 224 : 192);
  const int kg = 2 * j + (rb >> 3), tn = rb & 7;

  if (tid == 64) { PROF_EV(0); PROF_CK(40); }
  if (warp < 8) {
    asm volatile("barrier.cluster.arrive.relaxed.aligned;" ::: "memory");
    asm volatile("setmaxnreg.inc.sync.aligned.u32 192;");
    if (!helper) {
      const int wg = warp >> 2, w = warp & 3, g = lane >> 2;
      const bool elect = (tid & 127) == 0;
      float cX[32], cA[64], cB[64], cC[64], ci[64], ct[64];
      const int zero = blockIdx.x >> 16;
      uint32_t h[56], yf[16];
      const uint32_t d0 = (sb & 0x3FFFF) >> 4;
      const uint32_t dK = d0 | (1u << 16), dN = d0 | (512u << 16);
      const uint32_t dX = dK + wg * 512;
      constexpr uint32_t RING = OFF_RING >> 4;
      auto waitA = [&](int n) { mbar_wait(bars + 8 * (B_FA + rslot(n)), rpar(n)); };
      auto freeA = [&](int n) { mbar_arrive_if(elect, bars + 8 * (B_EA + rslot(n))); };
      auto nop = [] {};

      asm volatile("bar.sync 0, 384;" ::: "memory");
#pragma unroll 1
      for (int i = 0; i < 4; i++) {
        const uint64_t dx = d128(dX + i * 2048), df = d128(dK + (OFF_XB >> 4) + (i & 1) * 1024);
        mbar_wait(bars + 8 * (B_FX + 2 * i), 0);
        wg_fence();
        mma_ss64<0, 0, 2>(cX, df, dx, i);
        mma_ss64<0, 0, 1>(cX, df + 2, dx + 2);
        wg_commit(); wg_wait<1>();
        mbar_arrive_if(elect && i, bars + 8 * (B_EA + rslot(i - 1)));
        mma_ss64<0, 0, 1>(cX, df + 4, dx + 4);
        mma_ss64<0, 0, 1>(cX, df + 6, dx + 6);
        if (i == 0 && tid == 0) PROF_EV(1);
        mbar_wait(bars + 8 * (B_FX + 2 * i + 1), 0);
        wg_fence();
#pragma unroll
        for (int k = 0; k < 4; k++) mma_ss64<0, 0, 1>(cX, df + (512 + k * 2), dx + (1024 + k * 2));
        wg_commit();
        waitA(i);
        wg_fence();
        const uint64_t da = d128(dX + i * 1024), db = d128(dN + RING + i * 1024);
        mma_ss128<0, 1, 2>(cA, da, db, i);
        wg_commit(); wg_wait<1>();
        mbar_arrive_if(elect, bars + 8 * (B_FE + i));
#pragma unroll
        for (int k = 1; k < 4; k++) mma_ss128<0, 1, 1>(cA, da + k * 2, db + k * 128);
        wg_commit();
      }
      fence_regs<0, 32>(cX);
#pragma unroll
      for (int e = 0; e < 16; e++) yf[e] = pack_pin(cX[2 * e], cX[2 * e + 1]);
      if (tid == 0) PROF_EV(2);
      {
        waitA(4); mbar_wait(bars + 8 * B_E0, 0);
        const uint64_t de = d128(dN + (wg ? RING : OFF_XB >> 4));
        wg_fence();
        mma_rs128<0, 1, 0>(cB, yf[0], yf[1], yf[2], yf[3], de);
        wg_commit();
        wg_wait<1>();
        freeA(3);
#pragma unroll
        for (int k = 1; k < 4; k++) mma_rs128<0, 1, 1>(cB, yf[4 * k], yf[4 * k + 1], yf[4 * k + 2], yf[4 * k + 3], de + k * 128);
        wg_commit();
      }
      bool rel = false;
      auto acquire = [&](int n) {
        rel = elect;
        if (!mbar_try(bars + 8 * (B_FA + rslot(n)), rpar(n))) { wg_wait<0>(); freeA(n - 1); rel = false; waitA(n); }
      };
      auto freeP = [&](int n) { mbar_arrive_if(rel, bars + 8 * (B_EA + rslot(n - 1))); };
      auto ffn_step = [&](auto first, auto split, float (&acc)[64], int n, int kb, auto done, auto work) {
        constexpr int SPLIT = decltype(split)::value;
        acquire(n);
        wg_fence();
        const uint64_t dx = d128(dX + kb * 1024), db = d128(dN + RING + rslot(n) * 1024);
        mma_ss128<0, 1, decltype(first)::value>(acc, dx, db, zero);
#pragma unroll
        for (int k = 1; k < SPLIT; k++) mma_ss128<0, 1, 1>(acc, dx + k * 2, db + k * 128);
        wg_commit();
        work();
        wg_wait<1>();
        freeP(n);
        done();
        if (SPLIT < 4) {
          wg_fence();
#pragma unroll
          for (int k = SPLIT; k < 4; k++) mma_ss128<0, 1, 1>(acc, dx + k * 2, db + k * 128);
          wg_commit();
        }
      };
      {
        const int s0 = 2 * rb + wg, kr = 2 * ((s0 & 1) | ((s0 & 4) >> 1));
        const int m = lane >> 3, r = lane & 7;
        const uint32_t a0 = sb + OFF_XB + wg * 8192 + (((w >> 1) * 8 + (m >> 1)) * 2 + (w & 1)) * 256 + (m & 1) * 128 + ((r ^ (kr + (m & 1))) << 4);
        ffn_step(IC<1>(), IC<4>(), cA, 5, 4, [&] { fence_regs<0, 64>(cB); }, nop);
        asm volatile("bar.sync 5, 256;" ::: "memory");
#pragma unroll
        for (int i = 0; i < 4; i++)
          stsm4t(a0 + i * 1024, pack_bf16(cB[8 * i] - cB[34 + 8 * i], cB[8 * i + 1] - cB[35 + 8 * i]),
                 pack_bf16(cB[32 + 8 * i] + cB[8 * i + 2], cB[33 + 8 * i] + cB[8 * i + 3]),
                 pack_bf16(cB[8 * i + 4] - cB[38 + 8 * i], cB[8 * i + 5] - cB[39 + 8 * i]),
                 pack_bf16(cB[36 + 8 * i] + cB[8 * i + 6], cB[37 + 8 * i] + cB[8 * i + 7]));
        if (j == 0 && w == 0) {
          const uint32_t a1 = r ? sb + OFF_SP + 1024 : sb + OFF_SP + wg * 512 + (m & 1) * 256 + (m >> 1) * 128;
#pragma unroll
          for (int n = 0; n < 8; n++)
            asm volatile("stmatrix.sync.aligned.m8n8.x4.shared.b16 [%0], {%1,%2,%3,%4};" ::"r"(a1 + ((n ^ (kr + (m >> 1))) << 4)),
                         "r"(pack_bf16(cB[4 * n], cB[4 * n + 1])), "r"(pack_bf16(cB[4 * n + 2], cB[4 * n + 3])),
                         "r"(pack_bf16(cB[32 + 4 * n], cB[33 + 4 * n])), "r"(pack_bf16(cB[34 + 4 * n], cB[35 + 4 * n])) : "memory");
        }
        ffn_step(IC<1>(), IC<2>(), cA, 6, 5, nop, [&] {
          asm volatile("fence.proxy.async.shared::cta;" ::: "memory");
          __syncwarp();
          mbar_arrive_if(lane == 0, bars + 8 * (B_XS + wg));
          if (tid == 0) PROF_EV(3);
        });
      }
#pragma unroll 1
      for (int kb = 6; kb < 8; kb++) ffn_step(IC<1>(), IC<1>(), cA, 1 + kb, kb, nop, nop);
      ffn_step(IC<2>(), IC<1>(), cB, 9, 0, [&] { fence_regs<0, 64>(cA); }, nop);
#pragma unroll 1
      for (int kb = 1; kb < 6; kb++) ffn_step(IC<1>(), IC<1>(), cB, 9 + kb, kb, nop, nop);
      mbar_wait(bars + 8 * B_G, 0);
      const uint32_t gb0 = *(const uint32_t*)(smem + OFF_G + (wg * 64 + w * 16 + g) * 4), gb1 = *(const uint32_t*)(smem + OFF_G + (wg * 64 + w * 16 + g + 8) * 4);
      const uint32_t tag = gb0 & 1;
      const float g0 = __uint_as_float(gb0 & ~1u), g1 = __uint_as_float(gb1 & ~1u);
      const float o0 = 1.0f - g0, o1 = 1.0f - g1;
      auto glu = [&](auto& acc, int half, int ho, int i0, int i1) {
#pragma unroll
        for (int i = i0; i < i1; i++) {
          const float o = (i & 1) ? o1 : o0;
          h[ho + i] = pack_pin(fmaxf(acc[2 * i], 0.f) * acc[half + 2 * i] * o, fmaxf(acc[2 * i + 1], 0.f) * acc[half + 1 + 2 * i] * o);
        }
      };
      ffn_step(IC<1>(), IC<1>(), cB, 15, 6, nop, [&] { glu(cA, 32, 0, 0, 8); });
      ffn_step(IC<1>(), IC<1>(), cB, 16, 7, nop, [&] { glu(cA, 32, 0, 8, 16); });
      ffn_step(IC<0>(), IC<1>(), cC, 17, 0, [&] { fence_regs<0, 64>(cB); }, nop);
      if (tid == 0) PROF_EV(4);
      ffn_step(IC<1>(), IC<1>(), cC, 18, 1, nop, [&] { glu(cB, 32, 16, 0, 8); });
      ffn_step(IC<1>(), IC<1>(), cC, 19, 2, nop, [&] { glu(cB, 32, 16, 8, 16); });
#pragma unroll 1
      for (int kb = 3; kb < 8; kb++) ffn_step(IC<1>(), IC<1>(), cC, 17 + kb, kb, nop, nop);
      if (tid == 0) PROF_EV(5);
      auto m_step = [&](auto first, int i, auto done, auto work) {
        acquire(25 + i);
        wg_fence();
        const uint64_t dx = d128(dX + i * 2048), dm = d64(dN + RING + rslot(25 + i) * 1024);
        mma_ss64<0, 1, decltype(first)::value>(ct, dx, dm);
        mma_ss64<0, 1, 1>(ct, dx + 2, dm + 64);
        wg_commit();
        work();
        wg_wait<1>();
        freeP(25 + i);
        done();
        wg_fence();
#pragma unroll
        for (int k = 2; k < 8; k++) mma_ss64<0, 1, 1>(ct, dx + ((k >> 2) * 1024 + (k & 3) * 2), dm + k * 64);
        wg_commit();
      };
      auto freeT = [&](int t) { mbar_arrive_if(elect, bars + 8 * (B_ET + t)); };
      m_step(IC<0>(), 0, [&] { fence_regs<0, 64>(cC); }, nop);
      m_step(IC<1>(), 1, [&] { freeT(0); }, [&] { glu(cC, 32, 32, 0, 5); });
      m_step(IC<1>(), 2, [&] { freeT(1); }, [&] { glu(cC, 32, 32, 5, 11); });
      m_step(IC<1>(), 3, [&] { freeT(2); }, [&] { glu(cC, 32, 32, 11, 16); });
      waitA(29 + wg);
      if (tid == 0) PROF_EV(6);
      mbar_wait(bars + 8 * (j == 0 ? B_T : B_TL), 0);
      if (tid == 0) PROF_EV(7);
      wg_fence();
      {
        const uint64_t dt = d128(dN + (OFF_T >> 4) + wg * 512), de = d128(dK + RING + (1 + wg) * 1024);
        mma_ss64<0, 1, 0>(ci, de, dt);
        mma_ss64<32, 1, 0>(ci, de + 512, dt);
#pragma unroll
        for (int k = 1; k < 4; k++) {
          mma_ss64<0, 1, 1>(ci, de + k * 2, dt + k * 128);
          mma_ss64<32, 1, 1>(ci, de + (512 + k * 2), dt + k * 128);
        }
        wg_commit();
        wg_wait<1>();
        freeT(3);
        fence_regs<0, 32>(ct);
        glu(ct, 16, 48, 0, 8);
      }

      auto fetch_part = [&](uint4 (&pv)[4], int z) {
        mbar_wait(bars + 8 * (B_HP + z), 0);
#pragma unroll
        for (int i = 0; i < 4; i++) pv[i] = *(const uint4*)(smem + z * U + i * 4096 + tid * 16);
      };
      auto check_part = [&](uint4 (&pv)[4], int z) {
        const uint32_t t0 = (uint32_t)clock();
        while (__any_sync(0xffffffffu, ((pv[0].x ^ tag) | (pv[1].x ^ tag) | (pv[2].x ^ tag) | (pv[3].x ^ tag)) & 1)) {
#pragma unroll
          for (int i = 0; i < 4; i++) pv[i] = ld_x4(g_part + (size_t)((rb * 8 + j) * 3 + z) * 1024 + tid + i * 256);
          spin_guard(t0);
        }
#pragma unroll
        for (int i = 0; i < 4; i++) pv[i].x &= ~1u;
      };
      auto head = [&](auto off, int t) {
        constexpr int O = decltype(off)::value;
        const bool init = (t >= 3 && t < 6) || t == 7;
        if (init) {
          uint4 pv[4];
          if (O == 32 && t == 7) { fetch_part(pv, 0); check_part(pv, 0); }
          else {
            mbar_wait(bars + 8 * (B_Z + t - 3), 0);
#pragma unroll
            for (int i = 0; i < 4; i++) pv[i] = *(const uint4*)(smem + OFF_Z + (t - 3) * U + i * 4096 + tid * 16);
          }
#pragma unroll
          for (int i = 0; i < 4; i++) {
            const uint32_t a[4] = {pv[i].x, pv[i].y, pv[i].z, pv[i].w};
#pragma unroll
            for (int e = 0; e < 4; e++) { ct[O + 8 * i + 2 * e] = bf_lo(a[e]); ct[O + 8 * i + 2 * e + 1] = bf_hi(a[e]); }
          }
        }
        mbar_wait(bars + 8 * (B_FT + (t & 3)), t >> 2);
        const uint64_t db = d128(dN + (t & 3) * (TB >> 4) + rank * 256);
        wg_fence();
        mma_rs64<O, 1, 2>(ct, h[0], h[1], h[2], h[3], db, zero + init);
#pragma unroll
        for (int k = 1; k < HEADN; k++) mma_rs64<O, 1, 1>(ct, h[4 * k], h[4 * k + 1], h[4 * k + 2], h[4 * k + 3], db + k * 128);
        wg_commit();
        wg_wait<1>();
      };
      auto rest = [&](auto off, int t) {
        constexpr int O = decltype(off)::value;
        const uint64_t db = d128(dN + (t & 3) * (TB >> 4)), dw = db + rank * 256, dm = db + (rank ? 0 : 1536);
        wg_fence();
#pragma unroll
        for (int k = HEADN; k < 12; k++) mma_rs64<O, 1, 1>(ct, h[4 * k], h[4 * k + 1], h[4 * k + 2], h[4 * k + 3], dw + k * 128);
#pragma unroll
        for (int k = 0; k < 2; k++) mma_rs64<O, 1, 1>(ct, h[48 + 4 * k], h[49 + 4 * k], h[50 + 4 * k], h[51 + 4 * k], dm + k * 128);
#pragma unroll
        for (int k = 0; k < 4; k++) mma_rs64<O, 1, 1>(ct, yf[4 * k], yf[4 * k + 1], yf[4 * k + 2], yf[4 * k + 3], db + (14 + k) * 128);
        wg_commit();
      };
      const uint32_t peerZ = mapa(sb + OFF_Z + tid * 16, rank ^ 1), peerB = mapa(bars + 8 * B_Z, rank ^ 1);
      auto send = [&](auto off, int t) {
        constexpr int O = decltype(off)::value;
        fence_regs<O, 32>(ct);
        const bool grid = t >= 3 && t < 6;
        const int z = grid ? t - 3 : t == 6 ? 3 : t;
        uint32_t pk[16];
#pragma unroll
        for (int i = 0; i < 16; i++) pk[i] = pack_bf16(ct[O + 2 * i], ct[O + 2 * i + 1]);
        if (grid) {
          const int owner = rb * 8 + 2 * ((q4 + z + 1) & 3) + rank;
          uint4* dst = g_part + (size_t)(owner * 3 + z) * 1024 + tid;
#pragma unroll
          for (int i = 0; i < 4; i++) st_x4(dst + i * 256, (pk[4 * i] & ~1u) | tag, pk[4 * i + 1], pk[4 * i + 2], pk[4 * i + 3]);
          __syncwarp();
          hint_add_if(lane == 0, &g_cntP[32 * owner + z]);
        } else {
#pragma unroll
          for (int i = 0; i < 4; i++)
            asm volatile("st.async.weak.shared::cluster.mbarrier::complete_tx::bytes.v4.b32 [%0], {%1,%2,%3,%4}, [%5];" ::"r"(peerZ + z * U + i * 4096),
                         "r"(pk[4 * i]), "r"(pk[4 * i + 1]), "r"(pk[4 * i + 2]), "r"(pk[4 * i + 3]), "r"(peerB + 8 * z) : "memory");
        }
      };
      asm volatile("barrier.cluster.wait.aligned;" ::: "memory");
      head(IC<0>(), 0);
      if (elect) asm volatile("mbarrier.arrive.shared::cluster.b64 _, [%0];" ::"r"(mapa(bars + 8 * B_RDY, rank ^ 1)) : "memory");
      fence_regs<0, 64>(ci);
#pragma unroll
      for (int i = 0; i < 16; i++) {
        const float gg = ((i & 1) ? g1 : g0) * (2.0f / (2048.0f * 512.0f));
        if (i & 2) yf[i] = pack_pin((ci[2 * i] - ci[28 + 2 * i]) * gg, (ci[2 * i + 1] - ci[29 + 2 * i]) * gg);
        else yf[i] = pack_pin((ci[2 * i] + ci[36 + 2 * i]) * gg, (ci[2 * i + 1] + ci[37 + 2 * i]) * gg);
      }
      if (tid == 0) PROF_EV(8);
#pragma unroll 1
      for (int t = 0;; t += 2) {
        rest(IC<0>(), t);
        head(IC<32>(), t + 1);
        mbar_arrive_if(elect && t < 6, bars + 8 * (B_ET + t));
        if (t == 0) mbar_wait(bars + 8 * B_RDY, 0);
        send(IC<0>(), t);
        rest(IC<32>(), t + 1);
        if (t == 6) break;
        head(IC<0>(), t + 2);
        mbar_arrive_if(elect, bars + 8 * (B_ET + t + 1));
        send(IC<32>(), t + 1);
      }
      if (tid == 0) PROF_EV(9);
      {
        float sum[32];
        uint4 p1[4], p2[4], p3[4];
        fetch_part(p1, 1);
        mbar_wait(bars + 8 * (B_Z + 3), 0);
#pragma unroll
        for (int i = 0; i < 4; i++) p3[i] = *(const uint4*)(smem + OFF_Z + 3 * U + i * 4096 + tid * 16);
        if (tid == 0) PROF_EV(25);
        fetch_part(p2, 2);
        if (tid == 0) PROF_EV(24);
        check_part(p1, 1); check_part(p2, 2);
#pragma unroll
        for (int i = 0; i < 4; i++) {
          const uint32_t a[4] = {p1[i].x, p1[i].y, p1[i].z, p1[i].w}, b[4] = {p2[i].x, p2[i].y, p2[i].z, p2[i].w}, c[4] = {p3[i].x, p3[i].y, p3[i].z, p3[i].w};
#pragma unroll
          for (int e = 0; e < 4; e++) {
            sum[8 * i + 2 * e] = bf_lo(a[e]) + bf_lo(c[e]) + bf_lo(b[e]);
            sum[8 * i + 2 * e + 1] = bf_hi(a[e]) + bf_hi(c[e]) + bf_hi(b[e]);
          }
        }
        if (tid == 0) PROF_EV(14);
        wg_wait<0>();
        fence_regs<32, 32>(ct);
#pragma unroll
        for (int i = 0; i < 32; i++) sum[i] += ct[32 + i];
        const uint32_t stg = sb + OFF_T + warp * 2048;
        const int mr = (lane & 7) + ((lane >> 3) & 1) * 8, mc = lane >> 4;
#pragma unroll
        for (int i = 0; i < 4; i++) {
          const uint32_t a = stg + mr * 128 + (((2 * i + mc) ^ (mr & 7)) << 4);
          asm volatile("stmatrix.sync.aligned.m8n8.x4.shared.b16 [%0], {%1,%2,%3,%4};" ::"r"(a), "r"(pack_bf16(sum[8 * i], sum[8 * i + 1])),
                       "r"(pack_bf16(sum[8 * i + 2], sum[8 * i + 3])), "r"(pack_bf16(sum[8 * i + 4], sum[8 * i + 5])),
                       "r"(pack_bf16(sum[8 * i + 6], sum[8 * i + 7])) : "memory");
        }
        __syncwarp();
#pragma unroll
        for (int i = 0; i < 4; i++) {
          const int r = 4 * i + (lane >> 3), c = lane & 7;
          const uint4 v = *(const uint4*)(smem + OFF_T + warp * 2048 + r * 128 + ((c ^ (r & 7)) << 4));
          *(uint4*)(out + (size_t)(2 * rb + wg + 32 * (16 * w + r)) * 512 + 64 * j + 8 * c) = v;
        }
      }
      if (tid == 0) { PROF_EV(15); PROF_CK(41); }
    }
  } else if (warp < 12) {
    asm volatile("setmaxnreg.dec.sync.aligned.u32 104;");
    asm volatile("barrier.cluster.arrive.relaxed.aligned;" ::: "memory");
    const int t = tid - 256, w = warp - 8;
    const uint32_t ep = ld_x1(&g_epoch[blockIdx.x * 8]);
    const uint32_t tag = (ep + 1) & 1;
    auto w_issue = [&](const CUtensorMap* m) {
          if (elect_one()) { mbar_expect_tx(bars + 8 * (B_WR + w), 3072); tma4d(sb + OFF_T + w * 3072, m, bars + 8 * (B_WR + w), 16 * kg, 0, 2 * w, tn); }
          __syncwarp();
    };
    auto gate_rows = [&] {
      const int r = 16 * j + 4 * w + (lane >> 3);
      const uint4* pg = (const uint4*)gate_w + (lane & 7);
      {
        float a = 0.f;
        asm volatile("bar.sync 4, 256;" ::: "memory");
#pragma unroll 1
        for (int hf = 0; hf < 2; hf++) {
          uint4 v[4], u[4];
#pragma unroll
          for (int kb = 0; kb < 4; kb++) v[kb] = __ldg(pg + (4 * hf + kb) * 8);
          mbar_wait(bars + 8 * (B_FE + 1 + 2 * hf), 0);
          if (hf) w_issue(&maps.wr);
#pragma unroll
          for (int kb = 0; kb < 4; kb++) u[kb] = *(const uint4*)(smem + (4 * hf + kb) * U + r * 128 + (((lane ^ r) & 7) << 4));
#pragma unroll
          for (int kb = 0; kb < 4; kb++) {
            a = fmaf(bf_lo(u[kb].x), bf_lo(v[kb].x), a); a = fmaf(bf_hi(u[kb].x), bf_hi(v[kb].x), a);
            a = fmaf(bf_lo(u[kb].y), bf_lo(v[kb].y), a); a = fmaf(bf_hi(u[kb].y), bf_hi(v[kb].y), a);
            a = fmaf(bf_lo(u[kb].z), bf_lo(v[kb].z), a); a = fmaf(bf_hi(u[kb].z), bf_hi(v[kb].z), a);
            a = fmaf(bf_lo(u[kb].w), bf_lo(v[kb].w), a); a = fmaf(bf_hi(u[kb].w), bf_hi(v[kb].w), a);
          }
        }
#pragma unroll
        for (int o = 4; o; o >>= 1) a += __shfl_xor_sync(0xffffffffu, a, o);
        if ((lane & 7) == 0)
          asm volatile("st.relaxed.gpu.global.f32 [%0], %1;" ::"l"(g_gate + rb * 128 + r), "f"(tagf(__fdividef(1.0f, 1.0f + __expf(-a)), tag)) : "memory");
        if (t == 0) PROF_EV(18);
      }
    };
    {
      const int g = lane >> 2, q = lane & 3;
      uint32_t wf[32];
      if (!helper) {
        gate_rows();
        const uint32_t wa = sb + OFF_T + w * (3072 + 4) + q * 48 + g * 2;
#pragma unroll 1
        for (int ri = 0; ri < 2; ri++) {
          mbar_wait(bars + 8 * (B_WR + w), ri);
#pragma unroll
          for (int n2 = 0; n2 < 2; n2++) {
            uint32_t v[16];
#pragma unroll
            for (int i = 0; i < 16; i++)
              asm volatile("ld.shared.u16 %0, [%1];" : "=r"(v[i]) : "r"(wa + (4 * n2 + ((i >> 1) & 3)) * 192 + (i & 1) * (1536 + 2) + (i >> 3) * 16) : "memory");
#pragma unroll
            for (int i = 0; i < 16; i++) {
              uint32_t& d = wf[(i >> 3) * 16 + 8 * n2 + (i & 7)];
              d = __byte_perm(d, v[i], 0x5432);
              asm volatile("" : "+r"(d)::"memory");
            }
          }
          __syncwarp();
          if (ri == 0) w_issue(&maps.wi);
        }
        asm volatile("bar.sync 1, 128;" ::: "memory");
        if (t == 0) PROF_EV(11);
      } else {
        asm volatile("bar.sync 4, 256;" ::: "memory");
        hint_wait(&g_cntW[0], (ep + 1) * 128u);
        const uint32_t t0 = (uint32_t)clock();
#pragma unroll 1
        for (;;) {
          uint32_t bad = 0;
#pragma unroll
          for (int i = 0; i < 32; i++) {
            const float2 v = ld_x2((const float2*)g_Wh + (i >> 4) * 2048 + 16 * w + g + 8 * (i & 1) + 64 * q + ((i >> 1) & 7) * 256);
            wf[i] = __float_as_uint(v.x); bad |= __float_as_uint(v.y) ^ tag;
          }
          if (!__any_sync(0xffffffffu, bad & 1)) break;
          spin_guard(t0);
        }
        if (t == 0) PROF_EV(11);
      }
      if (w == 0 && elect_one()) { mbar_expect_tx(bars + 8 * B_W, 8192); bulk_load(sb + OFF_D, g_DT.v, 8192, bars + 8 * B_W); }
      if (!helper) {
        const uint32_t t0 = (uint32_t)clock();
        uint32_t v;
        do { v = ld_x1(g_gate + rb * 128 + t); spin_guard(t0); } while (__any_sync(0xffffffffu, (v ^ tag) & 1));
        *(uint32_t*)(smem + OFF_G + t * 4) = v;
        __syncwarp();
        mbar_arrive_if(lane == 0, bars + 8 * B_G);
      }
      mbar_wait(bars + 8 * B_W, 0);
      mbar_wait(bars + 8 * B_HX, 0);
      if (t == 0) PROF_EV(12);
      const uint32_t dd = (sb & 0x3FFFF) >> 4;
      const uint64_t dF = d128((dd + (OFF_D >> 4)) | (512u << 16)), dI = d128((dd + (OFF_D >> 4)) | (1u << 16)), dA = d128((dd + (OFF_XB >> 4)) | (512u << 16));
      float az[32];
      const int zero = blockIdx.x >> 16;
      uint32_t pf[32];
#pragma unroll
      for (int mt = 0; mt < 2; mt++) {
        wg_fence();
        if (mt == 0) mma_ss64<0, 3, 0>(az, dA, dF);
        else mma_ss64<0, 3, 2>(az, dA + 512, dF, zero);
#pragma unroll
        for (int k = 1; k < 4; k++) mma_ss64<0, 3, 1>(az, dA + (mt * 512 + k * 128), dF + k * 128);
        wg_commit();
        wg_wait<0>();
        fence_regs<0, 32>(az);
#pragma unroll
        for (int i = 0; i < 16; i++) {
          const float wr = bf_lo(wf[16 * mt + i]), wi = bf_hi(wf[16 * mt + i]);
          pf[16 * mt + i] = pack_pin(fmaf(az[2 * i], wr, -az[2 * i + 1] * wi), fmaf(az[2 * i], wi, az[2 * i + 1] * wr));
        }
      }
      if (t == 0) PROF_EV(16);
#pragma unroll
      for (int mt = 0; mt < 2; mt++) {
        wg_fence();
        mma_rs64<0, 0, 2>(az, pf[16 * mt], pf[16 * mt + 1], pf[16 * mt + 2], pf[16 * mt + 3], dI, mt ? (int)helper : zero);
#pragma unroll
        for (int k = 1; k < 4; k++) mma_rs64<0, 0, 1>(az, pf[16 * mt + 4 * k], pf[16 * mt + 4 * k + 1], pf[16 * mt + 4 * k + 2], pf[16 * mt + 4 * k + 3], dI + k * 2);
        wg_commit();
        wg_wait<0>();
        fence_regs<0, 32>(az);
        if (!helper) {
          const int m = lane >> 3, r = lane & 7;
          const int sl = 2 * (m >> 1) + ((r >> 1) & 1) + 4 * (r >> 2);
          const uint32_t a0 = sb + OFF_XB + (2 * w + (m & 1)) * 2048 + sl * 64 + (((mt * 2 + (r & 1)) ^ (sl >> 1)) << 4);
#pragma unroll
          for (int i = 0; i < 4; i++)
            stsm4t(a0 + i * 512, pack_bf16(az[8 * i], az[8 * i + 1]), pack_bf16(az[8 * i + 2], az[8 * i + 3]), pack_bf16(az[8 * i + 4], az[8 * i + 5]),
                   pack_bf16(az[8 * i + 6], az[8 * i + 7]));
        }
      }
      if (helper) {
#pragma unroll
        for (int i = 0; i < 16; i++) {
          const int n = i >> 1, s0 = 8 * (n >> 1) + 2 * (n & 1) + (q & 1) + 4 * (q >> 1);
          if ((n & 1) == (int)(blockIdx.x & 1)) st_u2(g_Ts + s0 * 64 + 16 * w + g + 8 * (i & 1), pack_bf16(az[2 * i], az[2 * i + 1]), tag);
        }
        __syncwarp();
        hint_add_if(lane == 0, &g_cntH[0]);
        if (t == 0) { g_epoch[blockIdx.x * 8] = ep + 1; PROF_EV(13); }
      } else {
        asm volatile("fence.proxy.async.shared::cta;" ::: "memory");
        __syncwarp();
        if (elect_one()) {
          if (t == 0) PROF_EV(17);
          if (SPACE) __nanosleep(SPACE * w);
          asm volatile("cp.async.bulk.tensor.3d.global.shared::cta.bulk_group [%0, {%2, %3, %4}], [%1];" ::"l"(&maps.ts), "r"(sb + OFF_XB + w * 4096),
                       "r"(32 * kg), "r"(0), "r"(8 * tn + 2 * w) : "memory");
          bulk_done_signal(&g_cntT[32 * j]);
          if (t == 96) PROF_EV(13);
        }
        __syncwarp();
        if (j == 0) {
          hint_wait(&g_cntH[0], (ep + 1) * 8u);
          const uint32_t t0 = (uint32_t)clock();
          float2 v;
          do { v = ld_x2((const float2*)g_Ts + 2 * rb * 64 + t); spin_guard(t0); } while (__any_sync(0xffffffffu, (__float_as_uint(v.y) ^ tag) & 1));
          mbar_wait(bars + 8 * B_TL, 0);
          const uint32_t u = __float_as_uint(v.x);
          *(uint16_t*)(smem + OFF_T + t * 128 + ((t & 7) << 4)) = (uint16_t)u;
          *(uint16_t*)(smem + OFF_T + t * 128 + (((t & 7) ^ 1) << 4)) = (uint16_t)(u >> 16);
          asm volatile("fence.proxy.async.shared::cta;" ::: "memory");
          __syncwarp();
          mbar_arrive_if(lane == 0, bars + 8 * B_T);
        }
      }
    }
  } else {
    asm volatile("setmaxnreg.dec.sync.aligned.u32 24;");
    auto xf_load = [&](int q) {
      const uint32_t fb = bars + 8 * (B_FX + q);
      mbar_expect_tx(fb, U + 8192);
      tma3d(sb + q * U, &maps.x, fb, 64 * q, 0, 2 * rb);
      if (q >= 4) mbar_wait(bars + 8 * (B_FE + ((q - 4) >> 1)), 0);
      tma2d(sb + OFF_XB + (q & 3) * 8192, &maps.ft, fb, 64 * q, 64 * j);
    };
    if (elect_one()) {
      if (warp == 14) {
#pragma unroll
        for (int i = 0; i < B_FT; i++) mbar_init(bars + 8 * i, 1);
        asm volatile("fence.proxy.async.shared::cta;" ::: "memory");
        if (!helper) {
#pragma unroll 1
          for (int n = 0; n < 2; n++) {
            const uint32_t fb = bars + 8 * (B_FA + n);
            xf_load(2 * n); xf_load(2 * n + 1);
            mbar_expect_tx(fb, U);
            tma2d(sb + OFF_RING + n * U, &maps.g64, fb, f_full, 64 * n);
            tma2d(sb + OFF_RING + n * U + 8192, &maps.u64, fb, f_full, 64 * n);
          }
        }
      } else if (warp == 15) {
#pragma unroll
        for (int i = B_FT; i < NBAR; i++) mbar_init(bars + 8 * i, i < B_EA ? 1 : i < B_T ? 2 : 4);
#pragma unroll
        for (int i = 0; i < 4; i++) mbar_expect_tx(bars + 8 * (B_Z + i), U);
        asm volatile("fence.mbarrier_init.release.cluster;" ::: "memory");
        asm volatile("fence.proxy.async.shared::cta;" ::: "memory");
      } else if (warp == 13) {
#pragma unroll
        for (int i = 1; i < 4; i++) asm volatile("prefetch.tensormap [%0];" ::"l"((const char*)&maps + i * 128) : "memory");
      }
    }
    __syncwarp();
    asm volatile("bar.arrive 0, 384;" ::: "memory");
    asm volatile("bar.arrive 4, 256;" ::: "memory");
    __syncwarp();
    asm volatile("barrier.cluster.arrive.relaxed.aligned;" ::: "memory");
    asm volatile("bar.sync 3, 128;" ::: "memory");
    if (warp == 15 && !helper) {
        mbar_wait(bars + 8 * B_FE, 0);
        const uint32_t tag = (ld_x1(&g_epoch[blockIdx.x * 8]) + 1) & 1;
        const int c = lane >> 4, jj = 16 * blockIdx.x + (lane & 15), jm = (2048 - jj) & 2047;
        const unsigned short* pr = (const unsigned short*)w_r + 256 * c;
        const unsigned short* pi = (const unsigned short*)w_i + 256 * c;
        const float wr = 0.25f * (bf_lo(__ldg(pr + jj * 257)) + bf_lo(__ldg(pr + jm * 257)));
        const float wi = 0.25f * (bf_lo(__ldg(pi + jj * 257)) - bf_lo(__ldg(pi + jm * 257)));
        st_u2(g_Wh + c * 2048 + jj, c ? pack_bf16(-wi, wr) : pack_bf16(wr, wi), tag);
        __syncwarp();
        hint_add_if(lane == 0, &g_cntW[0]);
      }
    if ((!helper || warp == 15) && elect_one()) {
      if (warp < 14) {
        const int p = warp - 12;
#pragma unroll 1
        for (int n = 2; n < 31; n++) {
          const bool table = n == 4 || n >= 29;
          const int q = n < 4 ? n : n - 1;
          const CUtensorMap* m = table ? &maps.e : n >= 25 ? &maps.g32 + p : &maps.g64 + p;
          const int c0 = table ? 0 : n >= 25 ? f_half : f_full + 64 * (q >> 3);
          const int c1 = table ? (2 * rb + ((n & 1) ^ 1)) * 128 + 64 * p : n >= 25 ? 128 * (n - 25) : 64 * (q & 7);
          const uint32_t fb = bars + 8 * (B_FA + (n & 3)), dst = sb + OFF_RING + (n & 3) * U + p * 8192;
          if (n < 4) mbar_wait(bars + 8 * (B_FE + n - 2), 0);
          else mbar_wait(bars + 8 * (B_EA + (n & 3)), ((n >> 2) & 1) ^ 1);
          tma2d(dst, m, fb, c0, c1);
          if (p == 0) mbar_expect_tx(fb, U);
        }
      } else if (warp == 15) {
        const unsigned ep1 = ld_x1(&g_epoch[blockIdx.x * 8]) + 1;
        flag_wait(&g_cntX[helper ? 0 : 32 * j], ep1 * 16u);
        PROF_EV(22);
        mbar_expect_tx(bars + 8 * B_HX, U);
        bulk_load(sb + OFF_XB, g_X + (size_t)(helper ? 128 : kg * 8 + tn) * 8192, U, bars + 8 * B_HX);
        if (!helper) {
          flag_wait(&g_cntT[32 * j], ep1 * 64u);
          PROF_EV(23);
          mbar_expect_tx(bars + 8 * B_TL, U);
          tma3d(sb + OFF_T, &maps.t, bars + 8 * B_TL, 64 * j, 0, 2 * rb);
#pragma unroll 1
          for (int i = 0; i < 3; i++) {
            mbar_wait(bars + 8 * (B_PZ + (i >> 1)), 0);
            flag_wait(&g_cntP[32 * (rb * 8 + j) + i], ep1 * 8u);
            if (i == 2) PROF_EV(26);
            mbar_expect_tx(bars + 8 * (B_HP + i), U);
            bulk_load(sb + i * U, g_part + (size_t)((rb * 8 + j) * 3 + i) * 1024, U, bars + 8 * (B_HP + i));
          }
          g_epoch[blockIdx.x * 8] = ep1;
        }
      } else {
#pragma unroll 1
        for (int q = 4; q < 8; q++) xf_load(q);
        mbar_wait(bars + 8 * (B_FE + 2), 0);
        mbar_expect_tx(bars + 8 * B_E0, U);
        tma2d(sb + OFF_XB, &maps.e, bars + 8 * B_E0, 0, 2 * rb * 128);
        tma2d(sb + OFF_XB + 8192, &maps.e, bars + 8 * B_E0, 0, 2 * rb * 128 + 64);
#pragma unroll 1
        for (int h2 = 0; h2 < 2; h2++) {
          const int s0 = 2 * rb + h2, sg = (s0 & ~6) | ((s0 & 2) << 1) | ((s0 & 4) >> 1);
          mbar_wait(bars + 8 * (B_XS + h2), 0);
#pragma unroll 1
          for (int c = 0; c < 2; c++) {
            asm volatile("cp.async.bulk.tensor.4d.global.shared::cta.bulk_group [%0, {%2, %3, %4, %5}], [%1];" ::"l"(&maps.xs),
                         "r"(sb + OFF_XB + h2 * 8192 + c * 4096), "r"(0), "r"(sg), "r"(0), "r"(16 * j + 8 * c) : "memory");
            if (j == 0)
              asm volatile("cp.async.bulk.global.shared::cta.bulk_group [%0], [%1], 256;" ::"l"(g_X + 128 * 8192 + c * 4096 + sg * 128),
                           "r"(sb + OFF_SP + h2 * 512 + c * 256) : "memory");
            if (SPACE && h2 + c < 2) __nanosleep(SPACE);
          }
        }
        bulk_done_signal(&g_cntX[32 * j]);
        PROF_EV(20);
#pragma unroll 1
        for (int t = 0; t < 8; t++) {
          const int i = t < 3 ? t + 1 : t < 6 ? t - 2 : 0;
          const int col = 64 * (2 * ((q4 + i) & 3) + ((t < 3 || t == 6) ? 1 - rank : rank));
          const uint32_t fb = bars + 8 * (B_FT + (t & 3)), dst = sb + (t & 3) * TB;
          mbar_wait(bars + 8 * (B_ET + (t == 2 ? 3 : t & 3)), t >> 2);
          mbar_expect_tx(fb, TB);
          tma2d(dst, &maps.d224, fb, col, 224 * j);
          if (t < 2) mbar_wait(bars + 8 * (B_ET + t + 1), 0);
          tma2d(dst + 28672, &maps.ft, fb, col, 64 * j);
        }
      }
    }
  }
}

typedef CUresult (*EncodeFn)(CUtensorMap*, CUtensorMapDataType, cuuint32_t, void*, const cuuint64_t*, const cuuint64_t*, const cuuint32_t*,
                             const cuuint32_t*, CUtensorMapInterleave, CUtensorMapSwizzle, CUtensorMapL2promotion, CUtensorMapFloatOOBfill);

static void encode(EncodeFn f, CUtensorMap* m, const void* base, int rank, const cuuint64_t* dims, const cuuint64_t* strides, const cuuint32_t* box,
                   CUtensorMapSwizzle sw) {
  cuuint32_t es[5] = {1, 1, 1, 1, 1};
  f(m, CU_TENSOR_MAP_DATA_TYPE_BFLOAT16, rank, (void*)base, dims, strides, box, es, CU_TENSOR_MAP_INTERLEAVE_NONE, sw,
    CU_TENSOR_MAP_L2_PROMOTION_L2_128B, CU_TENSOR_MAP_FLOAT_OOB_FILL_NONE);
}

extern "C" void kernel_launch(void* const* d_in, const int* in_sizes, int n_in, void* d_out, int out_size) {
  (void)in_sizes; (void)n_in; (void)out_size;
  const __nv_bfloat16* x = (const __nv_bfloat16*)d_in[0];
  const __nv_bfloat16* w_r = (const __nv_bfloat16*)d_in[1];
  const __nv_bfloat16* w_i = (const __nv_bfloat16*)d_in[2];
  const __nv_bfloat16* Wg = (const __nv_bfloat16*)d_in[4];
  const __nv_bfloat16* Wu = (const __nv_bfloat16*)d_in[5];
  const __nv_bfloat16* Wd = (const __nv_bfloat16*)d_in[6];
  const __nv_bfloat16* gw = (const __nv_bfloat16*)d_in[7];

  void* fp = nullptr; cudaDriverEntryPointQueryResult qr;
  cudaGetDriverEntryPoint("cuTensorMapEncodeTiled", &fp, cudaEnableDefault, &qr);
  EncodeFn enc = (EncodeFn)fp;
  void *pFT, *pET, *pX, *pT;
  cudaGetSymbolAddress(&pX, g_X); cudaGetSymbolAddress(&pT, g_T);
  cudaGetSymbolAddress(&pFT, g_FT); cudaGetSymbolAddress(&pET, g_ET);

  Maps mp;
  const CUtensorMapSwizzle S128 = CU_TENSOR_MAP_SWIZZLE_128B, S64 = CU_TENSOR_MAP_SWIZZLE_64B;
  { cuuint64_t d[3] = {512, 64, 32}, s[2] = {32768, 1024}; cuuint32_t b[3] = {64, 64, 2}; encode(enc, &mp.x, x, 3, d, s, b, S128); }
  { cuuint64_t d[2] = {512, 512}, s[1] = {1024}; cuuint32_t b[2] = {64, 64}; encode(enc, &mp.ft, pFT, 2, d, s, b, S128); }
  { cuuint64_t d[4] = {128, 32, 2, 129}, s[3] = {256, 8192, 16384}; cuuint32_t b[4] = {128, 1, 2, 8}; encode(enc, &mp.xs, pX, 4, d, s, b, CU_TENSOR_MAP_SWIZZLE_NONE); }
  { cuuint64_t d[3] = {512, 32, 64}, s[2] = {65536, 1024}; cuuint32_t b[3] = {32, 32, 2}; encode(enc, &mp.ts, pT, 3, d, s, b, S64); }
  { cuuint64_t d[3] = {512, 64, 32}, s[2] = {1024, 65536}; cuuint32_t b[3] = {64, 64, 2}; encode(enc, &mp.t, pT, 3, d, s, b, S128); }
  { cuuint64_t d[2] = {64, 4096}, s[1] = {128}; cuuint32_t b[2] = {64, 64}; encode(enc, &mp.e, pET, 2, d, s, b, S128); }
  { cuuint64_t d[2] = {1792, 512}, s[1] = {3584}; cuuint32_t b[2] = {64, 64}, b2[2] = {32, 128};
    encode(enc, &mp.g64, Wg, 2, d, s, b, S128); encode(enc, &mp.u64, Wu, 2, d, s, b, S128);
    encode(enc, &mp.g32, Wg, 2, d, s, b2, S64); encode(enc, &mp.u32, Wu, 2, d, s, b2, S64); }
  { cuuint64_t d[2] = {512, 1792}, s[1] = {1024}; cuuint32_t b[2] = {64, 224}; encode(enc, &mp.d224, Wd, 2, d, s, b, S128); }
  { cuuint64_t d[4] = {264, 32, 8, 8}, s[3] = {32896, 512, 4112}; cuuint32_t b[4] = {24, 32, 2, 1};
    encode(enc, &mp.wr, w_r, 4, d, s, b, CU_TENSOR_MAP_SWIZZLE_NONE); encode(enc, &mp.wi, w_i, 4, d, s, b, CU_TENSOR_MAP_SWIZZLE_NONE); }

  cudaFuncSetAttribute(fused_kernel, cudaFuncAttributeMaxDynamicSharedMemorySize, SMEM_BYTES);
  fused_kernel<<<NCTA, 512, SMEM_BYTES>>>(mp, w_r, w_i, gw, (__nv_bfloat16*)d_out);
}
```

```cpp
#include <cuda_runtime.h>
#include <cuda_bf16.h>
#include <cuda.h>
#include <stdint.h>

namespace tbl {
constexpr double PI = 3.14159265358979323846264338327950288;
constexpr double sin_s(double x) { double t = x, s = x; for (int n = 1; n < 12; n++) { t *= -x * x / ((2 * n) * (2 * n + 1)); s += t; } return s; }
constexpr double cos_s(double x) { double t = 1, s = 1; for (int n = 1; n < 12; n++) { t *= -x * x / ((2 * n - 1) * (2 * n)); s += t; } return s; }
constexpr double cos2048(int m) {
  m &= 2047; if (m > 1024) m = 2048 - m;
  bool neg = false; if (m > 512) { m = 1024 - m; neg = true; }
  double v = (m <= 256) ? cos_s(2 * PI * m / 2048) : sin_s(2 * PI * (512 - m) / 2048);
  return neg ? -v : v;
}
constexpr uint16_t to_bf16(double v) {
  if (v == 0) return 0;
  uint16_t s = 0; if (v < 0) { s = 0x8000; v = -v; }
  int e = 0; while (v >= 2) { v /= 2; e++; } while (v < 1) { v *= 2; e--; }
  double m = (v - 1) * 128; int mi = (int)m; double fr = m - mi;
  if (fr > 0.5 || (fr == 0.5 && (mi & 1))) mi++;
  if (mi == 128) { mi = 0; e++; }
  return (uint16_t)(s | ((e + 127) << 7) | mi);
}
struct CosT { uint16_t v[2048]; constexpr CosT() : v() { for (int i = 0; i < 2048; i++) v[i] = to_bf16(cos2048(i)); } };
struct alignas(1024) FT {
  uint16_t v[512 * 512];
  constexpr FT() : v() {
    CosT c;
    for (int r = 0; r < 512; r++) {
      int k = (r >> 4) * 8 + (r & 7), e = (r >> 3) & 1;
      int mul = 4 * k, add = e ? 512 : 0;
      if (k == 0 && e == 1) { mul = 1024; add = 0; }
      for (int d = 0; d < 512; d++) v[r * 512 + d] = c.v[(d * mul + add) & 2047];
    }
  }
};
struct alignas(1024) ET {
  uint16_t v[2048 * 128];
  constexpr ET() : v() {
    CosT c;
    for (int s = 0; s < 2048; s++)
      for (int j = 0; j < 64; j++) {
        const int o = (s & 31) * 8192 + (s >> 5) * 64 + j;
        v[o] = c.v[(s * j) & 2047]; v[o + 4096] = c.v[(s * j + 512) & 2047];
      }
  }
};
struct alignas(1024) DT {
  uint16_t v[64 * 64];
  constexpr DT() : v() {
    CosT c;
    for (int r = 0; r < 64; r++)
      for (int n = 0; n < 64; n++) {
        const int sg = r >> 1, s0 = (sg & ~6) | ((sg & 2) << 1) | ((sg & 4) >> 1), e = r & 1, f = n & 1;
        const int m = 64 * s0 * (n >> 1) + (e == f ? 0 : e ? -512 : 512);
        v[r * 64 + (((n >> 3) ^ (r & 7)) << 3) + (n & 7)] = c.v[m & 2047];
      }
  }
};
}

__device__ constexpr tbl::FT g_FT = tbl::FT();
__device__ constexpr tbl::ET g_ET = tbl::ET();
__device__ constexpr tbl::DT g_DT = tbl::DT();

__device__ __align__(1024) uint16_t g_X[129 * 8192];
__device__ __align__(1024) uint16_t g_T[32 * 64 * 512];
__device__ __align__(1024) uint2 g_Ts[32 * 64];
__device__ __align__(1024) uint4 g_part[128 * 3 * 1024];
__device__ __align__(16) float g_gate[16 * 128];
__device__ __align__(16) uint2 g_Wh[2 * 2048];
__device__ unsigned g_epoch[132 * 8];
__device__ unsigned g_cntX[8 * 32], g_cntT[8 * 32], g_cntP[128 * 32], g_cntW[32], g_cntH[32];
#define PROF_EV(i) do {} while (0)
#define PROF_CK(i) do {} while (0)

__device__ __forceinline__ uint32_t smem_u32(const void* p) { return (uint32_t)__cvta_generic_to_shared(p); }
__device__ __forceinline__ void mbar_init(uint32_t bar, uint32_t cnt) { asm volatile("mbarrier.init.shared::cta.b64 [%0], %1;" ::"r"(bar), "r"(cnt)); }
__device__ __forceinline__ void mbar_expect_tx(uint32_t bar, uint32_t bytes) { asm volatile("mbarrier.arrive.expect_tx.shared::cta.b64 _, [%0], %1;" ::"r"(bar), "r"(bytes) : "memory"); }
__device__ __forceinline__ void mbar_arrive(uint32_t bar) { asm volatile("mbarrier.arrive.shared::cta.b64 _, [%0];" ::"r"(bar) : "memory"); }
__device__ __forceinline__ bool elect_one() {
  uint32_t p;
  asm volatile("{\n.reg .pred p;\nelect.sync _|p, 0xffffffff;\nselp.u32 %0, 1, 0, p;\n}" : "=r"(p));
  return p;
}
__device__ __forceinline__ void mbar_arrive_if(bool p, uint32_t bar) {
  asm volatile("{\n.reg .pred p;\nsetp.ne.b32 p, %1, 0;\n@p mbarrier.arrive.shared::cta.b64 _, [%0];\n}" ::"r"(bar), "r"((int)p) : "memory");
}
__device__ __forceinline__ void hint_add_if(bool p, unsigned* a) {
  asm volatile("{\n.reg .pred p;\nsetp.ne.b32 p, %1, 0;\n@p red.relaxed.gpu.global.add.u32 [%0], 1;\n}" ::"l"(a), "r"((int)p) : "memory");
}
__device__ __forceinline__ bool mbar_try(uint32_t bar, uint32_t parity) {
  uint32_t ok;
  asm volatile("{\n.reg .pred p;\nmbarrier.test_wait.parity.shared::cta.b64 p, [%1], %2;\nselp.u32 %0, 1, 0, p;\n}" : "=r"(ok) : "r"(bar), "r"(parity) : "memory");
  return ok;
}
__device__ __forceinline__ void mbar_wait(uint32_t bar, uint32_t parity) {
  asm volatile(
      "{\n.reg .pred p;\n.reg .u32 n;\nmov.u32 n, 0;\n"
      "W_LOOP:\nmbarrier.try_wait.parity.shared::cta.b64 p, [%0], %1;\n@p bra W_DONE;\n"
      "add.u32 n, n, 1;\nsetp.lt.u32 p, n, 0x40000;\n@p bra W_LOOP;\ntrap;\nW_DONE:\n}" ::"r"(bar), "r"(parity) : "memory");
}
__device__ __forceinline__ void bulk_load(uint32_t dst, const void* src, uint32_t bytes, uint32_t bar) {
  asm volatile("cp.async.bulk.shared::cluster.global.mbarrier::complete_tx::bytes [%0], [%1], %2, [%3];" ::"r"(dst), "l"(src), "r"(bytes), "r"(bar) : "memory");
}
__device__ __forceinline__ void cp16(uint32_t dst, const void* src) { asm volatile("cp.async.cg.shared.global [%0], [%1], 16;" ::"r"(dst), "l"(src) : "memory"); }
__device__ __forceinline__ void spin_guard(uint32_t t0) { if ((uint32_t)clock() - t0 > (1u << 30)) __trap(); }
__device__ __forceinline__ float tagf(float v, uint32_t tag) { return __uint_as_float((__float_as_uint(v) & ~1u) | tag); }
__device__ __forceinline__ float untag(float v) { return __uint_as_float(__float_as_uint(v) & ~1u); }
__device__ __forceinline__ void st_x2(float2* p, float a, float b) { asm volatile("st.relaxed.gpu.global.v2.f32 [%0], {%1,%2};" ::"l"(p), "f"(a), "f"(b) : "memory"); }
__device__ __forceinline__ float2 ld_x2(const float2* p) { float2 v; asm volatile("ld.relaxed.gpu.global.v2.f32 {%0,%1}, [%2];" : "=f"(v.x), "=f"(v.y) : "l"(p) : "memory"); return v; }
__device__ __forceinline__ void st_u2(uint2* p, uint32_t a, uint32_t b) { asm volatile("st.relaxed.gpu.global.v2.u32 [%0], {%1,%2};" ::"l"(p), "r"(a), "r"(b) : "memory"); }
__device__ __forceinline__ void prefetch2d(const CUtensorMap* m, int c0, int c1) { asm volatile("cp.async.bulk.prefetch.tensor.2d.L2.global [%0, {%1, %2}];" ::"l"(m), "r"(c0), "r"(c1) : "memory"); }
__device__ __forceinline__ void prefetch1d(const void* p, uint32_t bytes) { asm volatile("cp.async.bulk.prefetch.L2.global [%0], %1;" ::"l"(p), "r"(bytes) : "memory"); }
__device__ __forceinline__ uint32_t ld_x1(const void* p) { uint32_t v; asm volatile("ld.relaxed.gpu.global.u32 %0, [%1];" : "=r"(v) : "l"(p) : "memory"); return v; }
__device__ __forceinline__ uint4 ld_x4(const void* p) { uint4 v; asm volatile("ld.relaxed.gpu.global.v4.u32 {%0,%1,%2,%3}, [%4];" : "=r"(v.x), "=r"(v.y), "=r"(v.z), "=r"(v.w) : "l"(p) : "memory"); return v; }
__device__ __forceinline__ void st_x4(void* p, uint32_t a, uint32_t b, uint32_t c, uint32_t d) { asm volatile("st.relaxed.gpu.global.v4.u32 [%0], {%1,%2,%3,%4};" ::"l"(p), "r"(a), "r"(b), "r"(c), "r"(d) : "memory"); }
__device__ __forceinline__ uint32_t mapa(uint32_t a, uint32_t cta) { uint32_t r; asm volatile("mapa.shared::cluster.u32 %0, %1, %2;" : "=r"(r) : "r"(a), "r"(cta)); return r; }
__device__ __forceinline__ void stsm4t(uint32_t a, uint32_t r0, uint32_t r1, uint32_t r2, uint32_t r3) {
  asm volatile("stmatrix.sync.aligned.m8n8.x4.trans.shared.b16 [%0], {%1,%2,%3,%4};" ::"r"(a), "r"(r0), "r"(r1), "r"(r2), "r"(r3) : "memory");
}
__device__ __forceinline__ void hint_add(unsigned* p) { asm volatile("red.relaxed.gpu.global.add.u32 [%0], 1;" ::"l"(p) : "memory"); }
__device__ __forceinline__ void hint_wait(const unsigned* p, unsigned target) {
  const uint32_t t0 = (uint32_t)clock();
  while ((int)(ld_x1(p) - target) < 0) spin_guard(t0);
}
__device__ __forceinline__ void bulk_done_signal(unsigned* p) {
  asm volatile("cp.async.bulk.commit_group;\ncp.async.bulk.wait_group 0;\nfence.proxy.async.global;" ::: "memory");
  hint_add(p);
}
__device__ __forceinline__ void flag_wait(const unsigned* p, unsigned target) {
  hint_wait(p, target);
  asm volatile("fence.proxy.async.global;" ::: "memory");
}
__device__ __forceinline__ void tma2d(uint32_t dst, const CUtensorMap* m, uint32_t bar, int c0, int c1) {
  asm volatile("cp.async.bulk.tensor.2d.shared::cluster.global.mbarrier::complete_tx::bytes [%0], [%1, {%3, %4}], [%2];" ::"r"(dst), "l"(m), "r"(bar), "r"(c0), "r"(c1) : "memory");
}
__device__ __forceinline__ void tma3d(uint32_t dst, const CUtensorMap* m, uint32_t bar, int c0, int c1, int c2) {
  asm volatile("cp.async.bulk.tensor.3d.shared::cluster.global.mbarrier::complete_tx::bytes [%0], [%1, {%3, %4, %5}], [%2];" ::"r"(dst), "l"(m), "r"(bar), "r"(c0), "r"(c1), "r"(c2) : "memory");
}
__device__ __forceinline__ void tma4d(uint32_t dst, const CUtensorMap* m, uint32_t bar, int c0, int c1, int c2, int c3) {
  asm volatile("cp.async.bulk.tensor.4d.shared::cluster.global.mbarrier::complete_tx::bytes [%0], [%1, {%3, %4, %5, %6}], [%2];" ::"r"(dst), "l"(m), "r"(bar), "r"(c0), "r"(c1), "r"(c2), "r"(c3) : "memory");
}
__device__ __forceinline__ void wg_fence() { asm volatile("wgmma.fence.sync.aligned;" ::: "memory"); }
__device__ __forceinline__ void wg_commit() { asm volatile("wgmma.commit_group.sync.aligned;" ::: "memory"); }
template <int N> __device__ __forceinline__ void wg_wait() { asm volatile("wgmma.wait_group.sync.aligned %0;" ::"n"(N) : "memory"); }
template <int O, int N, int NN> __device__ __forceinline__ void fence_regs(float (&d)[NN]) {
#pragma unroll
  for (int i = 0; i < N; i++) asm volatile("" : "+f"(d[O + i])::"memory");
}
__device__ __forceinline__ uint32_t pack_bf16(float lo, float hi) {
  uint32_t r; asm("cvt.rn.bf16x2.f32 %0, %1, %2;" : "=r"(r) : "f"(hi), "f"(lo)); return r;
}
__device__ __forceinline__ uint32_t pack_pin(float lo, float hi) {
  uint32_t r; asm volatile("cvt.rn.bf16x2.f32 %0, %1, %2;" : "=r"(r) : "f"(hi), "f"(lo) : "memory"); return r;
}
__device__ __forceinline__ float bf_lo(uint32_t u) { return __uint_as_float(u << 16); }
__device__ __forceinline__ float bf_hi(uint32_t u) { return __uint_as_float(u & 0xffff0000u); }

__device__ __forceinline__ uint64_t d128(uint32_t lo) { uint64_t d; asm("mov.b64 %0, {%1, 0x40000040};" : "=l"(d) : "r"(lo)); return d; }
__device__ __forceinline__ uint64_t d64(uint32_t lo) { uint64_t d; asm("mov.b64 %0, {%1, 0x80000020};" : "=l"(d) : "r"(lo)); return d; }
template<int O,int TB,int ACC,int NN> __device__ __forceinline__ void mma_ss64(float (&d)[NN], uint64_t da, uint64_t db, int sd = 0){
  if constexpr (ACC == 1) asm volatile("wgmma.mma_async.sync.aligned.m64n64k16.f32.bf16.bf16 {%0,%1,%2,%3,%4,%5,%6,%7,%8,%9,%10,%11,%12,%13,%14,%15,%16,%17,%18,%19,%20,%21,%22,%23,%24,%25,%26,%27,%28,%29,%30,%31}, %32, %33, 1, 1, 1, %35, %34;"
   : "+f"(d[O+0]), "+f"(d[O+1]), "+f"(d[O+2]), "+f"(d[O+3]), "+f"(d[O+4]), "+f"(d[O+5]), "+f"(d[O+6]), "+f"(d[O+7]), "+f"(d[O+8]), "+f"(d[O+9]), "+f"(d[O+10]), "+f"(d[O+11]), "+f"(d[O+12]), "+f"(d[O+13]), "+f"(d[O+14]), "+f"(d[O+15]), "+f"(d[O+16]), "+f"(d[O+17]), "+f"(d[O+18]), "+f"(d[O+19]), "+f"(d[O+20]), "+f"(d[O+21]), "+f"(d[O+22]), "+f"(d[O+23]), "+f"(d[O+24]), "+f"(d[O+25]), "+f"(d[O+26]), "+f"(d[O+27]), "+f"(d[O+28]), "+f"(d[O+29]), "+f"(d[O+30]), "+f"(d[O+31])
   : "l"(da), "l"(db), "n"(TB & 1), "n"(TB >> 1));
  else if constexpr (ACC == 0) asm volatile("wgmma.mma_async.sync.aligned.m64n64k16.f32.bf16.bf16 {%0,%1,%2,%3,%4,%5,%6,%7,%8,%9,%10,%11,%12,%13,%14,%15,%16,%17,%18,%19,%20,%21,%22,%23,%24,%25,%26,%27,%28,%29,%30,%31}, %32, %33, 0, 1, 1, %35, %34;"
   : "=f"(d[O+0]), "=f"(d[O+1]), "=f"(d[O+2]), "=f"(d[O+3]), "=f"(d[O+4]), "=f"(d[O+5]), "=f"(d[O+6]), "=f"(d[O+7]), "=f"(d[O+8]), "=f"(d[O+9]), "=f"(d[O+10]), "=f"(d[O+11]), "=f"(d[O+12]), "=f"(d[O+13]), "=f"(d[O+14]), "=f"(d[O+15]), "=f"(d[O+16]), "=f"(d[O+17]), "=f"(d[O+18]), "=f"(d[O+19]), "=f"(d[O+20]), "=f"(d[O+21]), "=f"(d[O+22]), "=f"(d[O+23]), "=f"(d[O+24]), "=f"(d[O+25]), "=f"(d[O+26]), "=f"(d[O+27]), "=f"(d[O+28]), "=f"(d[O+29]), "=f"(d[O+30]), "=f"(d[O+31])
   : "l"(da), "l"(db), "n"(TB & 1), "n"(TB >> 1));
  else asm volatile("{\n.reg .pred p;\nsetp.ne.b32 p, %36, 0;\nwgmma.mma_async.sync.aligned.m64n64k16.f32.bf16.bf16 {%0,%1,%2,%3,%4,%5,%6,%7,%8,%9,%10,%11,%12,%13,%14,%15,%16,%17,%18,%19,%20,%21,%22,%23,%24,%25,%26,%27,%28,%29,%30,%31}, %32, %33, p, 1, 1, %35, %34;\n}"
   : "+f"(d[O+0]), "+f"(d[O+1]), "+f"(d[O+2]), "+f"(d[O+3]), "+f"(d[O+4]), "+f"(d[O+5]), "+f"(d[O+6]), "+f"(d[O+7]), "+f"(d[O+8]), "+f"(d[O+9]), "+f"(d[O+10]), "+f"(d[O+11]), "+f"(d[O+12]), "+f"(d[O+13]), "+f"(d[O+14]), "+f"(d[O+15]), "+f"(d[O+16]), "+f"(d[O+17]), "+f"(d[O+18]), "+f"(d[O+19]), "+f"(d[O+20]), "+f"(d[O+21]), "+f"(d[O+22]), "+f"(d[O+23]), "+f"(d[O+24]), "+f"(d[O+25]), "+f"(d[O+26]), "+f"(d[O+27]), "+f"(d[O+28]), "+f"(d[O+29]), "+f"(d[O+30]), "+f"(d[O+31])
   : "l"(da), "l"(db), "n"(TB & 1), "n"(TB >> 1), "r"(sd));
}
template<int O,int TB,int ACC,int NN> __device__ __forceinline__ void mma_rs64(float (&d)[NN], uint32_t a0, uint32_t a1, uint32_t a2, uint32_t a3, uint64_t db, int sd = 0){
  if constexpr (ACC == 1) asm volatile("wgmma.mma_async.sync.aligned.m64n64k16.f32.bf16.bf16 {%0,%1,%2,%3,%4,%5,%6,%7,%8,%9,%10,%11,%12,%13,%14,%15,%16,%17,%18,%19,%20,%21,%22,%23,%24,%25,%26,%27,%28,%29,%30,%31}, {%32,%33,%34,%35}, %36, 1, 1, 1, %37;"
   : "+f"(d[O+0]), "+f"(d[O+1]), "+f"(d[O+2]), "+f"(d[O+3]), "+f"(d[O+4]), "+f"(d[O+5]), "+f"(d[O+6]), "+f"(d[O+7]), "+f"(d[O+8]), "+f"(d[O+9]), "+f"(d[O+10]), "+f"(d[O+11]), "+f"(d[O+12]), "+f"(d[O+13]), "+f"(d[O+14]), "+f"(d[O+15]), "+f"(d[O+16]), "+f"(d[O+17]), "+f"(d[O+18]), "+f"(d[O+19]), "+f"(d[O+20]), "+f"(d[O+21]), "+f"(d[O+22]), "+f"(d[O+23]), "+f"(d[O+24]), "+f"(d[O+25]), "+f"(d[O+26]), "+f"(d[O+27]), "+f"(d[O+28]), "+f"(d[O+29]), "+f"(d[O+30]), "+f"(d[O+31])
   : "r"(a0), "r"(a1), "r"(a2), "r"(a3), "l"(db), "n"(TB));
  else if constexpr (ACC == 0) asm volatile("wgmma.mma_async.sync.aligned.m64n64k16.f32.bf16.bf16 {%0,%1,%2,%3,%4,%5,%6,%7,%8,%9,%10,%11,%12,%13,%14,%15,%16,%17,%18,%19,%20,%21,%22,%23,%24,%25,%26,%27,%28,%29,%30,%31}, {%32,%33,%34,%35}, %36, 0, 1, 1, %37;"
   : "=f"(d[O+0]), "=f"(d[O+1]), "=f"(d[O+2]), "=f"(d[O+3]), "=f"(d[O+4]), "=f"(d[O+5]), "=f"(d[O+6]), "=f"(d[O+7]), "=f"(d[O+8]), "=f"(d[O+9]), "=f"(d[O+10]), "=f"(d[O+11]), "=f"(d[O+12]), "=f"(d[O+13]), "=f"(d[O+14]), "=f"(d[O+15]), "=f"(d[O+16]), "=f"(d[O+17]), "=f"(d[O+18]), "=f"(d[O+19]), "=f"(d[O+20]), "=f"(d[O+21]), "=f"(d[O+22]), "=f"(d[O+23]), "=f"(d[O+24]), "=f"(d[O+25]), "=f"(d[O+26]), "=f"(d[O+27]), "=f"(d[O+28]), "=f"(d[O+29]), "=f"(d[O+30]), "=f"(d[O+31])
   : "r"(a0), "r"(a1), "r"(a2), "r"(a3), "l"(db), "n"(TB));
  else asm volatile("{\n.reg .pred p;\nsetp.ne.b32 p, %38, 0;\nwgmma.mma_async.sync.aligned.m64n64k16.f32.bf16.bf16 {%0,%1,%2,%3,%4,%5,%6,%7,%8,%9,%10,%11,%12,%13,%14,%15,%16,%17,%18,%19,%20,%21,%22,%23,%24,%25,%26,%27,%28,%29,%30,%31}, {%32,%33,%34,%35}, %36, p, 1, 1, %37;\n}"
   : "+f"(d[O+0]), "+f"(d[O+1]), "+f"(d[O+2]), "+f"(d[O+3]), "+f"(d[O+4]), "+f"(d[O+5]), "+f"(d[O+6]), "+f"(d[O+7]), "+f"(d[O+8]), "+f"(d[O+9]), "+f"(d[O+10]), "+f"(d[O+11]), "+f"(d[O+12]), "+f"(d[O+13]), "+f"(d[O+14]), "+f"(d[O+15]), "+f"(d[O+16]), "+f"(d[O+17]), "+f"(d[O+18]), "+f"(d[O+19]), "+f"(d[O+20]), "+f"(d[O+21]), "+f"(d[O+22]), "+f"(d[O+23]), "+f"(d[O+24]), "+f"(d[O+25]), "+f"(d[O+26]), "+f"(d[O+27]), "+f"(d[O+28]), "+f"(d[O+29]), "+f"(d[O+30]), "+f"(d[O+31])
   : "r"(a0), "r"(a1), "r"(a2), "r"(a3), "l"(db), "n"(TB), "r"(sd));
}
template<int O,int TB,int ACC,int NN> __device__ __forceinline__ void mma_ss128(float (&d)[NN], uint64_t da, uint64_t db, int sd = 0){
  if constexpr (ACC == 1) asm volatile("wgmma.mma_async.sync.aligned.m64n128k16.f32.bf16.bf16 {%0,%1,%2,%3,%4,%5,%6,%7,%8,%9,%10,%11,%12,%13,%14,%15,%16,%17,%18,%19,%20,%21,%22,%23,%24,%25,%26,%27,%28,%29,%30,%31,%32,%33,%34,%35,%36,%37,%38,%39,%40,%41,%42,%43,%44,%45,%46,%47,%48,%49,%50,%51,%52,%53,%54,%55,%56,%57,%58,%59,%60,%61,%62,%63}, %64, %65, 1, 1, 1, %67, %66;"
   : "+f"(d[O+0]), "+f"(d[O+1]), "+f"(d[O+2]), "+f"(d[O+3]), "+f"(d[O+4]), "+f"(d[O+5]), "+f"(d[O+6]), "+f"(d[O+7]), "+f"(d[O+8]), "+f"(d[O+9]), "+f"(d[O+10]), "+f"(d[O+11]), "+f"(d[O+12]), "+f"(d[O+13]), "+f"(d[O+14]), "+f"(d[O+15]), "+f"(d[O+16]), "+f"(d[O+17]), "+f"(d[O+18]), "+f"(d[O+19]), "+f"(d[O+20]), "+f"(d[O+21]), "+f"(d[O+22]), "+f"(d[O+23]), "+f"(d[O+24]), "+f"(d[O+25]), "+f"(d[O+26]), "+f"(d[O+27]), "+f"(d[O+28]), "+f"(d[O+29]), "+f"(d[O+30]), "+f"(d[O+31]), "+f"(d[O+32]), "+f"(d[O+33]), "+f"(d[O+34]), "+f"(d[O+35]), "+f"(d[O+36]), "+f"(d[O+37]), "+f"(d[O+38]), "+f"(d[O+39]), "+f"(d[O+40]), "+f"(d[O+41]), "+f"(d[O+42]), "+f"(d[O+43]), "+f"(d[O+44]), "+f"(d[O+45]), "+f"(d[O+46]), "+f"(d[O+47]), "+f"(d[O+48]), "+f"(d[O+49]), "+f"(d[O+50]), "+f"(d[O+51]), "+f"(d[O+52]), "+f"(d[O+53]), "+f"(d[O+54]), "+f"(d[O+55]), "+f"(d[O+56]), "+f"(d[O+57]), "+f"(d[O+58]), "+f"(d[O+59]), "+f"(d[O+60]), "+f"(d[O+61]), "+f"(d[O+62]), "+f"(d[O+63])
   : "l"(da), "l"(db), "n"(TB & 1), "n"(TB >> 1));
  else if constexpr (ACC == 0) asm volatile("wgmma.mma_async.sync.aligned.m64n128k16.f32.bf16.bf16 {%0,%1,%2,%3,%4,%5,%6,%7,%8,%9,%10,%11,%12,%13,%14,%15,%16,%17,%18,%19,%20,%21,%22,%23,%24,%25,%26,%27,%28,%29,%30,%31,%32,%33,%34,%35,%36,%37,%38,%39,%40,%41,%42,%43,%44,%45,%46,%47,%48,%49,%50,%51,%52,%53,%54,%55,%56,%57,%58,%59,%60,%61,%62,%63}, %64, %65, 0, 1, 1, %67, %66;"
   : "=f"(d[O+0]), "=f"(d[O+1]), "=f"(d[O+2]), "=f"(d[O+3]), "=f"(d[O+4]), "=f"(d[O+5]), "=f"(d[O+6]), "=f"(d[O+7]), "=f"(d[O+8]), "=f"(d[O+9]), "=f"(d[O+10]), "=f"(d[O+11]), "=f"(d[O+12]), "=f"(d[O+13]), "=f"(d[O+14]), "=f"(d[O+15]), "=f"(d[O+16]), "=f"(d[O+17]), "=f"(d[O+18]), "=f"(d[O+19]), "=f"(d[O+20]), "=f"(d[O+21]), "=f"(d[O+22]), "=f"(d[O+23]), "=f"(d[O+24]), "=f"(d[O+25]), "=f"(d[O+26]), "=f"(d[O+27]), "=f"(d[O+28]), "=f"(d[O+29]), "=f"(d[O+30]), "=f"(d[O+31]), "=f"(d[O+32]), "=f"(d[O+33]), "=f"(d[O+34]), "=f"(d[O+35]), "=f"(d[O+36]), "=f"(d[O+37]), "=f"(d[O+38]), "=f"(d[O+39]), "=f"(d[O+40]), "=f"(d[O+41]), "=f"(d[O+42]), "=f"(d[O+43]), "=f"(d[O+44]), "=f"(d[O+45]), "=f"(d[O+46]), "=f"(d[O+47]), "=f"(d[O+48]), "=f"(d[O+49]), "=f"(d[O+50]), "=f"(d[O+51]), "=f"(d[O+52]), "=f"(d[O+53]), "=f"(d[O+54]), "=f"(d[O+55]), "=f"(d[O+56]), "=f"(d[O+57]), "=f"(d[O+58]), "=f"(d[O+59]), "=f"(d[O+60]), "=f"(d[O+61]), "=f"(d[O+62]), "=f"(d[O+63])
   : "l"(da), "l"(db), "n"(TB & 1), "n"(TB >> 1));
  else asm volatile("{\n.reg .pred p;\nsetp.ne.b32 p, %68, 0;\nwgmma.mma_async.sync.aligned.m64n128k16.f32.bf16.bf16 {%0,%1,%2,%3,%4,%5,%6,%7,%8,%9,%10,%11,%12,%13,%14,%15,%16,%17,%18,%19,%20,%21,%22,%23,%24,%25,%26,%27,%28,%29,%30,%31,%32,%33,%34,%35,%36,%37,%38,%39,%40,%41,%42,%43,%44,%45,%46,%47,%48,%49,%50,%51,%52,%53,%54,%55,%56,%57,%58,%59,%60,%61,%62,%63}, %64, %65, p, 1, 1, %67, %66;\n}"
   : "+f"(d[O+0]), "+f"(d[O+1]), "+f"(d[O+2]), "+f"(d[O+3]), "+f"(d[O+4]), "+f"(d[O+5]), "+f"(d[O+6]), "+f"(d[O+7]), "+f"(d[O+8]), "+f"(d[O+9]), "+f"(d[O+10]), "+f"(d[O+11]), "+f"(d[O+12]), "+f"(d[O+13]), "+f"(d[O+14]), "+f"(d[O+15]), "+f"(d[O+16]), "+f"(d[O+17]), "+f"(d[O+18]), "+f"(d[O+19]), "+f"(d[O+20]), "+f"(d[O+21]), "+f"(d[O+22]), "+f"(d[O+23]), "+f"(d[O+24]), "+f"(d[O+25]), "+f"(d[O+26]), "+f"(d[O+27]), "+f"(d[O+28]), "+f"(d[O+29]), "+f"(d[O+30]), "+f"(d[O+31]), "+f"(d[O+32]), "+f"(d[O+33]), "+f"(d[O+34]), "+f"(d[O+35]), "+f"(d[O+36]), "+f"(d[O+37]), "+f"(d[O+38]), "+f"(d[O+39]), "+f"(d[O+40]), "+f"(d[O+41]), "+f"(d[O+42]), "+f"(d[O+43]), "+f"(d[O+44]), "+f"(d[O+45]), "+f"(d[O+46]), "+f"(d[O+47]), "+f"(d[O+48]), "+f"(d[O+49]), "+f"(d[O+50]), "+f"(d[O+51]), "+f"(d[O+52]), "+f"(d[O+53]), "+f"(d[O+54]), "+f"(d[O+55]), "+f"(d[O+56]), "+f"(d[O+57]), "+f"(d[O+58]), "+f"(d[O+59]), "+f"(d[O+60]), "+f"(d[O+61]), "+f"(d[O+62]), "+f"(d[O+63])
   : "l"(da), "l"(db), "n"(TB & 1), "n"(TB >> 1), "r"(sd));
}
template<int O,int TB,int ACC,int NN> __device__ __forceinline__ void mma_rs128(float (&d)[NN], uint32_t a0, uint32_t a1, uint32_t a2, uint32_t a3, uint64_t db, int sd = 0){
  if constexpr (ACC == 1) asm volatile("wgmma.mma_async.sync.aligned.m64n128k16.f32.bf16.bf16 {%0,%1,%2,%3,%4,%5,%6,%7,%8,%9,%10,%11,%12,%13,%14,%15,%16,%17,%18,%19,%20,%21,%22,%23,%24,%25,%26,%27,%28,%29,%30,%31,%32,%33,%34,%35,%36,%37,%38,%39,%40,%41,%42,%43,%44,%45,%46,%47,%48,%49,%50,%51,%52,%53,%54,%55,%56,%57,%58,%59,%60,%61,%62,%63}, {%64,%65,%66,%67}, %68, 1, 1, 1, %69;"
   : "+f"(d[O+0]), "+f"(d[O+1]), "+f"(d[O+2]), "+f"(d[O+3]), "+f"(d[O+4]), "+f"(d[O+5]), "+f"(d[O+6]), "+f"(d[O+7]), "+f"(d[O+8]), "+f"(d[O+9]), "+f"(d[O+10]), "+f"(d[O+11]), "+f"(d[O+12]), "+f"(d[O+13]), "+f"(d[O+14]), "+f"(d[O+15]), "+f"(d[O+16]), "+f"(d[O+17]), "+f"(d[O+18]), "+f"(d[O+19]), "+f"(d[O+20]), "+f"(d[O+21]), "+f"(d[O+22]), "+f"(d[O+23]), "+f"(d[O+24]), "+f"(d[O+25]), "+f"(d[O+26]), "+f"(d[O+27]), "+f"(d[O+28]), "+f"(d[O+29]), "+f"(d[O+30]), "+f"(d[O+31]), "+f"(d[O+32]), "+f"(d[O+33]), "+f"(d[O+34]), "+f"(d[O+35]), "+f"(d[O+36]), "+f"(d[O+37]), "+f"(d[O+38]), "+f"(d[O+39]), "+f"(d[O+40]), "+f"(d[O+41]), "+f"(d[O+42]), "+f"(d[O+43]), "+f"(d[O+44]), "+f"(d[O+45]), "+f"(d[O+46]), "+f"(d[O+47]), "+f"(d[O+48]), "+f"(d[O+49]), "+f"(d[O+50]), "+f"(d[O+51]), "+f"(d[O+52]), "+f"(d[O+53]), "+f"(d[O+54]), "+f"(d[O+55]), "+f"(d[O+56]), "+f"(d[O+57]), "+f"(d[O+58]), "+f"(d[O+59]), "+f"(d[O+60]), "+f"(d[O+61]), "+f"(d[O+62]), "+f"(d[O+63])
   : "r"(a0), "r"(a1), "r"(a2), "r"(a3), "l"(db), "n"(TB));
  else if constexpr (ACC == 0) asm volatile("wgmma.mma_async.sync.aligned.m64n128k16.f32.bf16.bf16 {%0,%1,%2,%3,%4,%5,%6,%7,%8,%9,%10,%11,%12,%13,%14,%15,%16,%17,%18,%19,%20,%21,%22,%23,%24,%25,%26,%27,%28,%29,%30,%31,%32,%33,%34,%35,%36,%37,%38,%39,%40,%41,%42,%43,%44,%45,%46,%47,%48,%49,%50,%51,%52,%53,%54,%55,%56,%57,%58,%59,%60,%61,%62,%63}, {%64,%65,%66,%67}, %68, 0, 1, 1, %69;"
   : "=f"(d[O+0]), "=f"(d[O+1]), "=f"(d[O+2]), "=f"(d[O+3]), "=f"(d[O+4]), "=f"(d[O+5]), "=f"(d[O+6]), "=f"(d[O+7]), "=f"(d[O+8]), "=f"(d[O+9]), "=f"(d[O+10]), "=f"(d[O+11]), "=f"(d[O+12]), "=f"(d[O+13]), "=f"(d[O+14]), "=f"(d[O+15]), "=f"(d[O+16]), "=f"(d[O+17]), "=f"(d[O+18]), "=f"(d[O+19]), "=f"(d[O+20]), "=f"(d[O+21]), "=f"(d[O+22]), "=f"(d[O+23]), "=f"(d[O+24]), "=f"(d[O+25]), "=f"(d[O+26]), "=f"(d[O+27]), "=f"(d[O+28]), "=f"(d[O+29]), "=f"(d[O+30]), "=f"(d[O+31]), "=f"(d[O+32]), "=f"(d[O+33]), "=f"(d[O+34]), "=f"(d[O+35]), "=f"(d[O+36]), "=f"(d[O+37]), "=f"(d[O+38]), "=f"(d[O+39]), "=f"(d[O+40]), "=f"(d[O+41]), "=f"(d[O+42]), "=f"(d[O+43]), "=f"(d[O+44]), "=f"(d[O+45]), "=f"(d[O+46]), "=f"(d[O+47]), "=f"(d[O+48]), "=f"(d[O+49]), "=f"(d[O+50]), "=f"(d[O+51]), "=f"(d[O+52]), "=f"(d[O+53]), "=f"(d[O+54]), "=f"(d[O+55]), "=f"(d[O+56]), "=f"(d[O+57]), "=f"(d[O+58]), "=f"(d[O+59]), "=f"(d[O+60]), "=f"(d[O+61]), "=f"(d[O+62]), "=f"(d[O+63])
   : "r"(a0), "r"(a1), "r"(a2), "r"(a3), "l"(db), "n"(TB));
  else asm volatile("{\n.reg .pred p;\nsetp.ne.b32 p, %70, 0;\nwgmma.mma_async.sync.aligned.m64n128k16.f32.bf16.bf16 {%0,%1,%2,%3,%4,%5,%6,%7,%8,%9,%10,%11,%12,%13,%14,%15,%16,%17,%18,%19,%20,%21,%22,%23,%24,%25,%26,%27,%28,%29,%30,%31,%32,%33,%34,%35,%36,%37,%38,%39,%40,%41,%42,%43,%44,%45,%46,%47,%48,%49,%50,%51,%52,%53,%54,%55,%56,%57,%58,%59,%60,%61,%62,%63}, {%64,%65,%66,%67}, %68, p, 1, 1, %69;\n}"
   : "+f"(d[O+0]), "+f"(d[O+1]), "+f"(d[O+2]), "+f"(d[O+3]), "+f"(d[O+4]), "+f"(d[O+5]), "+f"(d[O+6]), "+f"(d[O+7]), "+f"(d[O+8]), "+f"(d[O+9]), "+f"(d[O+10]), "+f"(d[O+11]), "+f"(d[O+12]), "+f"(d[O+13]), "+f"(d[O+14]), "+f"(d[O+15]), "+f"(d[O+16]), "+f"(d[O+17]), "+f"(d[O+18]), "+f"(d[O+19]), "+f"(d[O+20]), "+f"(d[O+21]), "+f"(d[O+22]), "+f"(d[O+23]), "+f"(d[O+24]), "+f"(d[O+25]), "+f"(d[O+26]), "+f"(d[O+27]), "+f"(d[O+28]), "+f"(d[O+29]), "+f"(d[O+30]), "+f"(d[O+31]), "+f"(d[O+32]), "+f"(d[O+33]), "+f"(d[O+34]), "+f"(d[O+35]), "+f"(d[O+36]), "+f"(d[O+37]), "+f"(d[O+38]), "+f"(d[O+39]), "+f"(d[O+40]), "+f"(d[O+41]), "+f"(d[O+42]), "+f"(d[O+43]), "+f"(d[O+44]), "+f"(d[O+45]), "+f"(d[O+46]), "+f"(d[O+47]), "+f"(d[O+48]), "+f"(d[O+49]), "+f"(d[O+50]), "+f"(d[O+51]), "+f"(d[O+52]), "+f"(d[O+53]), "+f"(d[O+54]), "+f"(d[O+55]), "+f"(d[O+56]), "+f"(d[O+57]), "+f"(d[O+58]), "+f"(d[O+59]), "+f"(d[O+60]), "+f"(d[O+61]), "+f"(d[O+62]), "+f"(d[O+63])
   : "r"(a0), "r"(a1), "r"(a2), "r"(a3), "l"(db), "n"(TB), "r"(sd));
}

#define NEARLY 0
#define XAHEAD 3
#define HEADN 6
#define WBATCH 1
#define SPACE 0
#define WPF 1
#define WAFTER 7
#define WPACE 0
#define GATE_AT 4
#define TPACE 40
#define PFMODE 0
#define MAPMODE 0
template <int V> struct IC { static constexpr int value = V; };
struct Maps { CUtensorMap x, ft, g64, u64, e, wr, wi, xs, ts, t, g32, u32, d224; };

constexpr int NCTA = 130;
constexpr int U = 16384;
constexpr int TB = 36864;
constexpr int OFF_RING = 8 * U, OFF_Z = 9 * U, OFF_XB = 12 * U, OFF_T = 13 * U, OFF_D = OFF_T;
constexpr int OFF_BAR = 14 * U, OFF_SP = OFF_BAR + 512, OFF_G = OFF_SP + 1024 + 128;
constexpr int SMEM_BYTES = OFF_G + 512;
constexpr int B_FX = 0, B_FA = 8, B_FT = 12, B_Z = 16, B_W = 20, B_HX = 21, B_TL = 22, B_HP = 23, B_WR = 26, B_E0 = 30;
constexpr int B_EA = 31, B_ET = 35, B_PZ = 39, B_RDY = 41, B_FE = 42;
constexpr int B_T = 46, B_XS = 47, B_G = 49, NBAR = 50;
__host__ __device__ constexpr int rslot(int n) { return n & 3; }
__host__ __device__ constexpr int rpar(int n) { return (n >> 2) & 1; }

__global__ void __cluster_dims__(2, 1, 1) __launch_bounds__(512, 1)
fused_kernel(const __grid_constant__ Maps maps, const __nv_bfloat16* __restrict__ w_r,
             const __nv_bfloat16* __restrict__ w_i, const __nv_bfloat16* __restrict__ gate_w, __nv_bfloat16* __restrict__ out) {
  extern __shared__ __align__(1024) uint8_t smem[];
  const uint32_t sb = smem_u32(smem);
  const uint32_t bars = sb + OFF_BAR;
  const int tid = threadIdx.x, lane = tid & 31;
  const int warp = __shfl_sync(0xffffffffu, tid >> 5, 0);
  const bool helper = blockIdx.x >= 128;
  const int cl = (blockIdx.x >> 1) & 63, rank = blockIdx.x & 1;
  const int q4 = cl & 3, rb = cl >> 2;
  const int j = 2 * q4 + rank;
  const int f_full = 448 * q4 + (rank ? 256 : 0);
  const int f_half = 448 * q4 + (rank ? 224 : 192);
  const int kg = 2 * j + (rb >> 3), tn = rb & 7;

  if (tid == 64) { PROF_EV(0); PROF_CK(40); }
  if (warp < 8) {
    asm volatile("barrier.cluster.arrive.relaxed.aligned;" ::: "memory");
    asm volatile("setmaxnreg.inc.sync.aligned.u32 192;");
    if (!helper) {
      const int wg = warp >> 2, w = warp & 3, g = lane >> 2;
      const bool elect = (tid & 127) == 0;
      float cX[32], cA[64], cB[64], cC[64], ci[64], ct[64];
      const int zero = blockIdx.x >> 16;
      uint32_t h[56], yf[16];
      const uint32_t d0 = (sb & 0x3FFFF) >> 4;
      const uint32_t dK = d0 | (1u << 16), dN = d0 | (512u << 16);
      const uint32_t dX = dK + wg * 512;
      constexpr uint32_t RING = OFF_RING >> 4;
      auto waitA = [&](int n) { mbar_wait(bars + 8 * (B_FA + rslot(n)), rpar(n)); };
      auto freeA = [&](int n) { mbar_arrive_if(elect, bars + 8 * (B_EA + rslot(n))); };
      auto nop = [] {};

      asm volatile("bar.sync 0, 384;" ::: "memory");
#pragma unroll 1
      for (int i = 0; i < 4; i++) {
        const uint64_t dx = d128(dX + i * 2048), df = d128(dK + (OFF_XB >> 4) + (i & 1) * 1024);
        mbar_wait(bars + 8 * (B_FX + 2 * i), 0);
        wg_fence();
        mma_ss64<0, 0, 2>(cX, df, dx, i);
        mma_ss64<0, 0, 1>(cX, df + 2, dx + 2);
        wg_commit(); wg_wait<1>();
        mbar_arrive_if(elect && i, bars + 8 * (B_EA + rslot(i - 1)));
        mma_ss64<0, 0, 1>(cX, df + 4, dx + 4);
        mma_ss64<0, 0, 1>(cX, df + 6, dx + 6);
        if (i == 0 && tid == 0) PROF_EV(1);
        mbar_wait(bars + 8 * (B_FX + 2 * i + 1), 0);
        wg_fence();
#pragma unroll
        for (int k = 0; k < 4; k++) mma_ss64<0, 0, 1>(cX, df + (512 + k * 2), dx + (1024 + k * 2));
        wg_commit();
        waitA(i);
        wg_fence();
        const uint64_t da = d128(dX + i * 1024), db = d128(dN + RING + i * 1024);
        mma_ss128<0, 1, 2>(cA, da, db, i);
        wg_commit(); wg_wait<1>();
        mbar_arrive_if(elect, bars + 8 * (B_FE + i));
#pragma unroll
        for (int k = 1; k < 4; k++) mma_ss128<0, 1, 1>(cA, da + k * 2, db + k * 128);
        wg_commit();
      }
      fence_regs<0, 32>(cX);
#pragma unroll
      for (int e = 0; e < 16; e++) yf[e] = pack_pin(cX[2 * e], cX[2 * e + 1]);
      if (tid == 0) PROF_EV(2);
      {
        waitA(4); mbar_wait(bars + 8 * B_E0, 0);
        const uint64_t de = d128(dN + (wg ? RING : OFF_XB >> 4));
        wg_fence();
        mma_rs128<0, 1, 0>(cB, yf[0], yf[1], yf[2], yf[3], de);
        wg_commit();
        wg_wait<1>();
        freeA(3);
#pragma unroll
        for (int k = 1; k < 4; k++) mma_rs128<0, 1, 1>(cB, yf[4 * k], yf[4 * k + 1], yf[4 * k + 2], yf[4 * k + 3], de + k * 128);
        wg_commit();
      }
      bool rel = false;
      auto acquire = [&](int n) {
        rel = elect;
        if (!mbar_try(bars + 8 * (B_FA + rslot(n)), rpar(n))) { wg_wait<0>(); freeA(n - 1); rel = false; waitA(n); }
      };
      auto freeP = [&](int n) { mbar_arrive_if(rel, bars + 8 * (B_EA + rslot(n - 1))); };
      auto ffn_step = [&](auto first, auto split, float (&acc)[64], int n, int kb, auto done, auto work) {
        constexpr int SPLIT = decltype(split)::value;
        acquire(n);
        wg_fence();
        const uint64_t dx = d128(dX + kb * 1024), db = d128(dN + RING + rslot(n) * 1024);
        mma_ss128<0, 1, decltype(first)::value>(acc, dx, db, kb);
#pragma unroll
        for (int k = 1; k < SPLIT; k++) mma_ss128<0, 1, 1>(acc, dx + k * 2, db + k * 128);
        wg_commit();
        work();
        wg_wait<1>();
        freeP(n);
        done();
        if (SPLIT < 4) {
          wg_fence();
#pragma unroll
          for (int k = SPLIT; k < 4; k++) mma_ss128<0, 1, 1>(acc, dx + k * 2, db + k * 128);
          wg_commit();
        }
      };
      {
        const int s0 = 2 * rb + wg, kr = 2 * ((s0 & 1) | ((s0 & 4) >> 1));
        const int m = lane >> 3, r = lane & 7;
        const uint32_t a0 = sb + OFF_XB + wg * 8192 + (((w >> 1) * 8 + (m >> 1)) * 2 + (w & 1)) * 256 + (m & 1) * 128 + ((r ^ (kr + (m & 1))) << 4);
        ffn_step(IC<1>(), IC<4>(), cA, 5, 4, [&] { fence_regs<0, 64>(cB); }, nop);
        asm volatile("bar.sync 5, 256;" ::: "memory");
#pragma unroll
        for (int i = 0; i < 4; i++)
          stsm4t(a0 + i * 1024, pack_bf16(cB[8 * i] - cB[34 + 8 * i], cB[8 * i + 1] - cB[35 + 8 * i]),
                 pack_bf16(cB[32 + 8 * i] + cB[8 * i + 2], cB[33 + 8 * i] + cB[8 * i + 3]),
                 pack_bf16(cB[8 * i + 4] - cB[38 + 8 * i], cB[8 * i + 5] - cB[39 + 8 * i]),
                 pack_bf16(cB[36 + 8 * i] + cB[8 * i + 6], cB[37 + 8 * i] + cB[8 * i + 7]));
        if (j == 0 && w == 0) {
          const uint32_t a1 = r ? sb + OFF_SP + 1024 : sb + OFF_SP + wg * 512 + (m & 1) * 256 + (m >> 1) * 128;
#pragma unroll
          for (int n = 0; n < 8; n++)
            asm volatile("stmatrix.sync.aligned.m8n8.x4.shared.b16 [%0], {%1,%2,%3,%4};" ::"r"(a1 + ((n ^ (kr + (m >> 1))) << 4)),
                         "r"(pack_bf16(cB[4 * n], cB[4 * n + 1])), "r"(pack_bf16(cB[4 * n + 2], cB[4 * n + 3])),
                         "r"(pack_bf16(cB[32 + 4 * n], cB[33 + 4 * n])), "r"(pack_bf16(cB[34 + 4 * n], cB[35 + 4 * n])) : "memory");
        }
        ffn_step(IC<1>(), IC<2>(), cA, 6, 5, nop, [&] {
          asm volatile("fence.proxy.async.shared::cta;" ::: "memory");
          __syncwarp();
          mbar_arrive_if(lane == 0, bars + 8 * (B_XS + wg));
          if (tid == 0) PROF_EV(3);
        });
      }
#pragma unroll 1
      for (int kb = 6; kb < 8; kb++) ffn_step(IC<1>(), IC<1>(), cA, 1 + kb, kb, nop, nop);
      float g0 = 0.f, g1 = 0.f;
      uint32_t tag = 0;
      auto glu = [&](auto& acc, int half, int ho, int i0, int i1) {
#pragma unroll
        for (int i = i0; i < i1; i++) {
          const float o = 1.0f - ((i & 1) ? g1 : g0);
          asm volatile("" : "+f"(acc[2 * i]), "+f"(acc[2 * i + 1]), "+f"(acc[half + 2 * i]), "+f"(acc[half + 1 + 2 * i])::"memory");
          h[ho + i] = pack_pin(fmaxf(acc[2 * i], 0.f) * acc[half + 2 * i] * o, fmaxf(acc[2 * i + 1], 0.f) * acc[half + 1 + 2 * i] * o);
        }
      };
      ffn_step(IC<2>(), IC<1>(), cB, 9, zero, nop, nop);
#pragma unroll 1
      for (int kb = 1; kb < 8; kb++)
        ffn_step(IC<1>(), IC<1>(), cB, 9 + kb, kb, nop, [&] {
          if (kb == 4 + wg) {
            mbar_wait(bars + 8 * B_G, 0);
            const uint32_t gb0 = *(const uint32_t*)(smem + OFF_G + (wg * 64 + w * 16 + g) * 4), gb1 = *(const uint32_t*)(smem + OFF_G + (wg * 64 + w * 16 + g + 8) * 4);
            tag = gb0 & 1; g0 = __uint_as_float(gb0 & ~1u); g1 = __uint_as_float(gb1 & ~1u);
            glu(cA, 32, 0, 0, 8);
          } else if (kb == 6 + wg) glu(cA, 32, 0, 8, 16);
        });
      if (tid == 0) PROF_EV(4);
      ffn_step(IC<0>(), IC<1>(), cC, 17, 0, nop, nop);
#pragma unroll 1
      for (int kb = 1; kb < 8; kb++)
        ffn_step(IC<1>(), IC<1>(), cC, 17 + kb, kb, nop, [&] {
          if (kb == 1 + wg) glu(cB, 32, 16, 0, 8);
          else if (kb == 3 + wg) glu(cB, 32, 16, 8, 16);
        });
      if (tid == 0) PROF_EV(5);
      auto m_step = [&](auto first, int kb, auto work) {
        const int n = 25 + (kb >> 1);
        if (!(kb & 1)) acquire(n);
        wg_fence();
        const uint64_t dx = d128(dX + kb * 1024), dm = d64(dN + RING + rslot(n) * 1024 + (kb & 1) * 256);
        mma_ss64<0, 1, decltype(first)::value>(ct, dx, dm);
        mma_ss64<0, 1, 1>(ct, dx + 2, dm + 64);
        wg_commit();
        work();
        wg_wait<1>();
        mbar_arrive_if(rel && !(kb & 1), bars + 8 * (B_EA + rslot(n - 1)));
        mbar_arrive_if(elect && kb && !(kb & 1), bars + 8 * (B_ET + (kb >> 1) - 1));
        wg_fence();
        mma_ss64<0, 1, 1>(ct, dx + 4, dm + 128);
        mma_ss64<0, 1, 1>(ct, dx + 6, dm + 192);
        wg_commit();
      };
      auto freeT = [&](int t) { mbar_arrive_if(elect, bars + 8 * (B_ET + t)); };
      m_step(IC<0>(), 0, nop);
#pragma unroll 1
      for (int kb = 1; kb < 8; kb++)
        m_step(IC<1>(), kb, [&] {
          if (kb == 1 + 2 * wg) glu(cC, 32, 32, 0, 8);
          else if (kb == 5 + 2 * wg) glu(cC, 32, 32, 8, 16);
        });
      waitA(29 + wg);
      if (tid == 0) PROF_EV(6);
      mbar_wait(bars + 8 * (j == 0 ? B_T : B_TL), 0);
      if (tid == 0) PROF_EV(7);
      wg_fence();
      {
        const uint64_t dt = d128(dN + (OFF_T >> 4) + wg * 512), de = d128(dK + RING + (1 + wg) * 1024);
        mma_ss64<0, 1, 0>(ci, de, dt);
        mma_ss64<32, 1, 0>(ci, de + 512, dt);
#pragma unroll
        for (int k = 1; k < 4; k++) {
          mma_ss64<0, 1, 1>(ci, de + k * 2, dt + k * 128);
          mma_ss64<32, 1, 1>(ci, de + (512 + k * 2), dt + k * 128);
        }
        wg_commit();
        wg_wait<1>();
        freeT(3);
        fence_regs<0, 32>(ct);
        glu(ct, 16, 48, 0, 8);
      }

      auto fetch_part = [&](uint4 (&pv)[4], int z) {
        mbar_wait(bars + 8 * (B_HP + z), 0);
#pragma unroll
        for (int i = 0; i < 4; i++) pv[i] = *(const uint4*)(smem + z * U + i * 4096 + tid * 16);
      };
      auto check_part = [&](uint4 (&pv)[4], int z) {
        const uint32_t t0 = (uint32_t)clock();
        while (__any_sync(0xffffffffu, ((pv[0].x ^ tag) | (pv[1].x ^ tag) | (pv[2].x ^ tag) | (pv[3].x ^ tag)) & 1)) {
#pragma unroll
          for (int i = 0; i < 4; i++) pv[i] = ld_x4(g_part + (size_t)((rb * 8 + j) * 3 + z) * 1024 + tid + i * 256);
          spin_guard(t0);
        }
#pragma unroll
        for (int i = 0; i < 4; i++) pv[i].x &= ~1u;
      };
      auto head = [&](auto off, int t) {
        constexpr int O = decltype(off)::value;
        const bool init = (t >= 3 && t < 6) || t == 7;
        if (init) {
          uint4 pv[4];
          if (O == 32 && t == 7) { fetch_part(pv, 0); check_part(pv, 0); }
          else {
            mbar_wait(bars + 8 * (B_Z + t - 3), 0);
#pragma unroll
            for (int i = 0; i < 4; i++) pv[i] = *(const uint4*)(smem + OFF_Z + (t - 3) * U + i * 4096 + tid * 16);
          }
#pragma unroll
          for (int i = 0; i < 4; i++) {
            const uint32_t a[4] = {pv[i].x, pv[i].y, pv[i].z, pv[i].w};
#pragma unroll
            for (int e = 0; e < 4; e++) { ct[O + 8 * i + 2 * e] = bf_lo(a[e]); ct[O + 8 * i + 2 * e + 1] = bf_hi(a[e]); }
          }
        }
        mbar_wait(bars + 8 * (B_FT + (t & 3)), t >> 2);
        const uint64_t db = d128(dN + (t & 3) * (TB >> 4) + rank * 256);
        wg_fence();
        mma_rs64<O, 1, 2>(ct, h[0], h[1], h[2], h[3], db, zero + init);
#pragma unroll
        for (int k = 1; k < HEADN; k++) mma_rs64<O, 1, 1>(ct, h[4 * k], h[4 * k + 1], h[4 * k + 2], h[4 * k + 3], db + k * 128);
        wg_commit();
        wg_wait<1>();
      };
      auto rest = [&](auto off, int t) {
        constexpr int O = decltype(off)::value;
        const uint64_t db = d128(dN + (t & 3) * (TB >> 4)), dw = db + rank * 256, dm = db + (rank ? 0 : 1536);
        wg_fence();
#pragma unroll
        for (int k = HEADN; k < 12; k++) mma_rs64<O, 1, 1>(ct, h[4 * k], h[4 * k + 1], h[4 * k + 2], h[4 * k + 3], dw + k * 128);
#pragma unroll
        for (int k = 0; k < 2; k++) mma_rs64<O, 1, 1>(ct, h[48 + 4 * k], h[49 + 4 * k], h[50 + 4 * k], h[51 + 4 * k], dm + k * 128);
#pragma unroll
        for (int k = 0; k < 4; k++) mma_rs64<O, 1, 1>(ct, yf[4 * k], yf[4 * k + 1], yf[4 * k + 2], yf[4 * k + 3], db + (14 + k) * 128);
        wg_commit();
      };
      const uint32_t peerZ = mapa(sb + OFF_Z + tid * 16, rank ^ 1), peerB = mapa(bars + 8 * B_Z, rank ^ 1);
      auto send = [&](auto off, int t) {
        constexpr int O = decltype(off)::value;
        fence_regs<O, 32>(ct);
        const bool grid = t >= 3 && t < 6;
        const int z = grid ? t - 3 : t == 6 ? 3 : t;
        uint32_t pk[16];
#pragma unroll
        for (int i = 0; i < 16; i++) pk[i] = pack_bf16(ct[O + 2 * i], ct[O + 2 * i + 1]);
        if (grid) {
          const int owner = rb * 8 + 2 * ((q4 + z + 1) & 3) + rank;
          uint4* dst = g_part + (size_t)(owner * 3 + z) * 1024 + tid;
#pragma unroll
          for (int i = 0; i < 4; i++) st_x4(dst + i * 256, (pk[4 * i] & ~1u) | tag, pk[4 * i + 1], pk[4 * i + 2], pk[4 * i + 3]);
          __syncwarp();
          hint_add_if(lane == 0, &g_cntP[32 * owner + z]);
        } else {
#pragma unroll
          for (int i = 0; i < 4; i++)
            asm volatile("st.async.weak.shared::cluster.mbarrier::complete_tx::bytes.v4.b32 [%0], {%1,%2,%3,%4}, [%5];" ::"r"(peerZ + z * U + i * 4096),
                         "r"(pk[4 * i]), "r"(pk[4 * i + 1]), "r"(pk[4 * i + 2]), "r"(pk[4 * i + 3]), "r"(peerB + 8 * z) : "memory");
        }
      };
      asm volatile("barrier.cluster.wait.aligned;" ::: "memory");
      head(IC<0>(), 0);
      if (elect) asm volatile("mbarrier.arrive.shared::cluster.b64 _, [%0];" ::"r"(mapa(bars + 8 * B_RDY, rank ^ 1)) : "memory");
      fence_regs<0, 64>(ci);
#pragma unroll
      for (int i = 0; i < 16; i++) {
        const float gg = ((i & 1) ? g1 : g0) * (2.0f / (2048.0f * 512.0f));
        if (i & 2) yf[i] = pack_pin((ci[2 * i] - ci[28 + 2 * i]) * gg, (ci[2 * i + 1] - ci[29 + 2 * i]) * gg);
        else yf[i] = pack_pin((ci[2 * i] + ci[36 + 2 * i]) * gg, (ci[2 * i + 1] + ci[37 + 2 * i]) * gg);
      }
      if (tid == 0) PROF_EV(8);
#pragma unroll 1
      for (int t = 0;; t += 2) {
        rest(IC<0>(), t);
        head(IC<32>(), t + 1);
        mbar_arrive_if(elect && t < 6, bars + 8 * (B_ET + t));
        if (t == 0) mbar_wait(bars + 8 * B_RDY, 0);
        send(IC<0>(), t);
        rest(IC<32>(), t + 1);
        if (t == 6) break;
        head(IC<0>(), t + 2);
        mbar_arrive_if(elect, bars + 8 * (B_ET + t + 1));
        send(IC<32>(), t + 1);
      }
      if (tid == 0) PROF_EV(9);
      {
        float sum[32];
        uint4 p1[4], p2[4], p3[4];
        fetch_part(p1, 1);
        mbar_wait(bars + 8 * (B_Z + 3), 0);
#pragma unroll
        for (int i = 0; i < 4; i++) p3[i] = *(const uint4*)(smem + OFF_Z + 3 * U + i * 4096 + tid * 16);
        if (tid == 0) PROF_EV(25);
        fetch_part(p2, 2);
        if (tid == 0) PROF_EV(24);
        check_part(p1, 1); check_part(p2, 2);
#pragma unroll
        for (int i = 0; i < 4; i++) {
          const uint32_t a[4] = {p1[i].x, p1[i].y, p1[i].z, p1[i].w}, b[4] = {p2[i].x, p2[i].y, p2[i].z, p2[i].w}, c[4] = {p3[i].x, p3[i].y, p3[i].z, p3[i].w};
#pragma unroll
          for (int e = 0; e < 4; e++) {
            sum[8 * i + 2 * e] = bf_lo(a[e]) + bf_lo(c[e]) + bf_lo(b[e]);
            sum[8 * i + 2 * e + 1] = bf_hi(a[e]) + bf_hi(c[e]) + bf_hi(b[e]);
          }
        }
        if (tid == 0) PROF_EV(14);
        wg_wait<0>();
        fence_regs<32, 32>(ct);
#pragma unroll
        for (int i = 0; i < 32; i++) sum[i] += ct[32 + i];
        const uint32_t stg = sb + OFF_T + warp * 2048;
        const int mr = (lane & 7) + ((lane >> 3) & 1) * 8, mc = lane >> 4;
#pragma unroll
        for (int i = 0; i < 4; i++) {
          const uint32_t a = stg + mr * 128 + (((2 * i + mc) ^ (mr & 7)) << 4);
          asm volatile("stmatrix.sync.aligned.m8n8.x4.shared.b16 [%0], {%1,%2,%3,%4};" ::"r"(a), "r"(pack_bf16(sum[8 * i], sum[8 * i + 1])),
                       "r"(pack_bf16(sum[8 * i + 2], sum[8 * i + 3])), "r"(pack_bf16(sum[8 * i + 4], sum[8 * i + 5])),
                       "r"(pack_bf16(sum[8 * i + 6], sum[8 * i + 7])) : "memory");
        }
        __syncwarp();
#pragma unroll
        for (int i = 0; i < 4; i++) {
          const int r = 4 * i + (lane >> 3), c = lane & 7;
          const uint4 v = *(const uint4*)(smem + OFF_T + warp * 2048 + r * 128 + ((c ^ (r & 7)) << 4));
          *(uint4*)(out + (size_t)(2 * rb + wg + 32 * (16 * w + r)) * 512 + 64 * j + 8 * c) = v;
        }
      }
      if (tid == 0) { PROF_EV(15); PROF_CK(41); }
    }
  } else if (warp < 12) {
    asm volatile("setmaxnreg.dec.sync.aligned.u32 104;");
    asm volatile("barrier.cluster.arrive.relaxed.aligned;" ::: "memory");
    const int t = tid - 256, w = warp - 8;
    const uint32_t ep = ld_x1(&g_epoch[blockIdx.x * 8]);
    const uint32_t tag = (ep + 1) & 1;
    auto w_issue = [&](const CUtensorMap* m) {
          if (elect_one()) { mbar_expect_tx(bars + 8 * (B_WR + w), 3072); tma4d(sb + OFF_T + w * 3072, m, bars + 8 * (B_WR + w), 16 * kg, 0, 2 * w, tn); }
          __syncwarp();
    };
    auto gate_rows = [&] {
      const int r = 16 * j + 4 * w + (lane >> 3);
      const uint4* pg = (const uint4*)gate_w + (lane & 7);
      {
        float a = 0.f;
        asm volatile("bar.sync 4, 256;" ::: "memory");
#pragma unroll 1
        for (int hf = 0; hf < 2; hf++) {
          uint4 v[4], u[4];
#pragma unroll
          for (int kb = 0; kb < 4; kb++) v[kb] = __ldg(pg + (4 * hf + kb) * 8);
          mbar_wait(bars + 8 * (B_FE + 1 + 2 * hf), 0);
          if (hf) w_issue(&maps.wr);
#pragma unroll
          for (int kb = 0; kb < 4; kb++) u[kb] = *(const uint4*)(smem + (4 * hf + kb) * U + r * 128 + (((lane ^ r) & 7) << 4));
#pragma unroll
          for (int kb = 0; kb < 4; kb++) {
            a = fmaf(bf_lo(u[kb].x), bf_lo(v[kb].x), a); a = fmaf(bf_hi(u[kb].x), bf_hi(v[kb].x), a);
            a = fmaf(bf_lo(u[kb].y), bf_lo(v[kb].y), a); a = fmaf(bf_hi(u[kb].y), bf_hi(v[kb].y), a);
            a = fmaf(bf_lo(u[kb].z), bf_lo(v[kb].z), a); a = fmaf(bf_hi(u[kb].z), bf_hi(v[kb].z), a);
            a = fmaf(bf_lo(u[kb].w), bf_lo(v[kb].w), a); a = fmaf(bf_hi(u[kb].w), bf_hi(v[kb].w), a);
          }
        }
#pragma unroll
        for (int o = 4; o; o >>= 1) a += __shfl_xor_sync(0xffffffffu, a, o);
        if ((lane & 7) == 0)
          asm volatile("st.relaxed.gpu.global.f32 [%0], %1;" ::"l"(g_gate + rb * 128 + r), "f"(tagf(__fdividef(1.0f, 1.0f + __expf(-a)), tag)) : "memory");
        if (t == 0) PROF_EV(18);
      }
    };
    {
      const int g = lane >> 2, q = lane & 3;
      uint32_t wf[32];
      if (!helper) {
        gate_rows();
        const uint32_t wa = sb + OFF_T + w * (3072 + 4) + q * 48 + g * 2;
#pragma unroll 1
        for (int ri = 0; ri < 2; ri++) {
          mbar_wait(bars + 8 * (B_WR + w), ri);
#pragma unroll
          for (int n2 = 0; n2 < 2; n2++) {
            uint32_t v[16];
#pragma unroll
            for (int i = 0; i < 16; i++)
              asm volatile("ld.shared.u16 %0, [%1];" : "=r"(v[i]) : "r"(wa + (4 * n2 + ((i >> 1) & 3)) * 192 + (i & 1) * (1536 + 2) + (i >> 3) * 16) : "memory");
#pragma unroll
            for (int i = 0; i < 16; i++) {
              uint32_t& d = wf[(i >> 3) * 16 + 8 * n2 + (i & 7)];
              d = __byte_perm(d, v[i], 0x5432);
              asm volatile("" : "+r"(d)::"memory");
            }
          }
          __syncwarp();
          if (ri == 0) w_issue(&maps.wi);
        }
        asm volatile("bar.sync 1, 128;" ::: "memory");
        if (t == 0) PROF_EV(11);
      } else {
        asm volatile("bar.sync 4, 256;" ::: "memory");
        hint_wait(&g_cntW[0], (ep + 1) * 128u);
        const uint32_t t0 = (uint32_t)clock();
#pragma unroll 1
        for (;;) {
          uint32_t bad = 0;
#pragma unroll
          for (int i = 0; i < 32; i++) {
            const float2 v = ld_x2((const float2*)g_Wh + (i >> 4) * 2048 + 16 * w + g + 8 * (i & 1) + 64 * q + ((i >> 1) & 7) * 256);
            wf[i] = __float_as_uint(v.x); bad |= __float_as_uint(v.y) ^ tag;
          }
          if (!__any_sync(0xffffffffu, bad & 1)) break;
          spin_guard(t0);
        }
        if (t == 0) PROF_EV(11);
      }
      if (w == 0 && elect_one()) { mbar_expect_tx(bars + 8 * B_W, 8192); bulk_load(sb + OFF_D, g_DT.v, 8192, bars + 8 * B_W); }
      if (!helper) {
        const uint32_t t0 = (uint32_t)clock();
        uint32_t v;
        do { v = ld_x1(g_gate + rb * 128 + t); spin_guard(t0); } while (__any_sync(0xffffffffu, (v ^ tag) & 1));
        *(uint32_t*)(smem + OFF_G + t * 4) = v;
        __syncwarp();
        mbar_arrive_if(lane == 0, bars + 8 * B_G);
      }
      mbar_wait(bars + 8 * B_W, 0);
      mbar_wait(bars + 8 * B_HX, 0);
      if (t == 0) PROF_EV(12);
      const uint32_t dd = (sb & 0x3FFFF) >> 4;
      const uint64_t dF = d128((dd + (OFF_D >> 4)) | (512u << 16)), dI = d128((dd + (OFF_D >> 4)) | (1u << 16)), dA = d128((dd + (OFF_XB >> 4)) | (512u << 16));
      float az[32];
      const int zero = blockIdx.x >> 16;
      uint32_t pf[32];
#pragma unroll
      for (int mt = 0; mt < 2; mt++) {
        wg_fence();
        if (mt == 0) mma_ss64<0, 3, 0>(az, dA, dF);
        else mma_ss64<0, 3, 2>(az, dA + 512, dF, zero);
#pragma unroll
        for (int k = 1; k < 4; k++) mma_ss64<0, 3, 1>(az, dA + (mt * 512 + k * 128), dF + k * 128);
        wg_commit();
        wg_wait<0>();
        fence_regs<0, 32>(az);
#pragma unroll
        for (int i = 0; i < 16; i++) {
          const float wr = bf_lo(wf[16 * mt + i]), wi = bf_hi(wf[16 * mt + i]);
          pf[16 * mt + i] = pack_pin(fmaf(az[2 * i], wr, -az[2 * i + 1] * wi), fmaf(az[2 * i], wi, az[2 * i + 1] * wr));
        }
      }
      if (t == 0) PROF_EV(16);
#pragma unroll
      for (int mt = 0; mt < 2; mt++) {
        wg_fence();
        mma_rs64<0, 0, 2>(az, pf[16 * mt], pf[16 * mt + 1], pf[16 * mt + 2], pf[16 * mt + 3], dI, mt ? (int)helper : zero);
#pragma unroll
        for (int k = 1; k < 4; k++) mma_rs64<0, 0, 1>(az, pf[16 * mt + 4 * k], pf[16 * mt + 4 * k + 1], pf[16 * mt + 4 * k + 2], pf[16 * mt + 4 * k + 3], dI + k * 2);
        wg_commit();
        wg_wait<0>();
        fence_regs<0, 32>(az);
        if (!helper) {
          const int m = lane >> 3, r = lane & 7;
          const int sl = 2 * (m >> 1) + ((r >> 1) & 1) + 4 * (r >> 2);
          const uint32_t a0 = sb + OFF_XB + (2 * w + (m & 1)) * 2048 + sl * 64 + (((mt * 2 + (r & 1)) ^ (sl >> 1)) << 4);
#pragma unroll
          for (int i = 0; i < 4; i++)
            stsm4t(a0 + i * 512, pack_bf16(az[8 * i], az[8 * i + 1]), pack_bf16(az[8 * i + 2], az[8 * i + 3]), pack_bf16(az[8 * i + 4], az[8 * i + 5]),
                   pack_bf16(az[8 * i + 6], az[8 * i + 7]));
        }
      }
      if (helper) {
#pragma unroll
        for (int i = 0; i < 16; i++) {
          const int n = i >> 1, s0 = 8 * (n >> 1) + 2 * (n & 1) + (q & 1) + 4 * (q >> 1);
          if ((n & 1) == (int)(blockIdx.x & 1)) st_u2(g_Ts + s0 * 64 + 16 * w + g + 8 * (i & 1), pack_bf16(az[2 * i], az[2 * i + 1]), tag);
        }
        __syncwarp();
        hint_add_if(lane == 0, &g_cntH[0]);
        if (t == 0) { g_epoch[blockIdx.x * 8] = ep + 1; PROF_EV(13); }
      } else {
        asm volatile("fence.proxy.async.shared::cta;" ::: "memory");
        __syncwarp();
        if (elect_one()) {
          if (t == 0) PROF_EV(17);
          if (SPACE) __nanosleep(SPACE * w);
          asm volatile("cp.async.bulk.tensor.3d.global.shared::cta.bulk_group [%0, {%2, %3, %4}], [%1];" ::"l"(&maps.ts), "r"(sb + OFF_XB + w * 4096),
                       "r"(32 * kg), "r"(0), "r"(8 * tn + 2 * w) : "memory");
          bulk_done_signal(&g_cntT[32 * j]);
          if (t == 96) PROF_EV(13);
        }
        __syncwarp();
        if (j == 0) {
          hint_wait(&g_cntH[0], (ep + 1) * 8u);
          const uint32_t t0 = (uint32_t)clock();
          float2 v;
          do { v = ld_x2((const float2*)g_Ts + 2 * rb * 64 + t); spin_guard(t0); } while (__any_sync(0xffffffffu, (__float_as_uint(v.y) ^ tag) & 1));
          mbar_wait(bars + 8 * B_TL, 0);
          const uint32_t u = __float_as_uint(v.x);
          *(uint16_t*)(smem + OFF_T + t * 128 + ((t & 7) << 4)) = (uint16_t)u;
          *(uint16_t*)(smem + OFF_T + t * 128 + (((t & 7) ^ 1) << 4)) = (uint16_t)(u >> 16);
          asm volatile("fence.proxy.async.shared::cta;" ::: "memory");
          __syncwarp();
          mbar_arrive_if(lane == 0, bars + 8 * B_T);
        }
      }
    }
  } else {
    asm volatile("setmaxnreg.dec.sync.aligned.u32 24;");
    auto xf_load = [&](int q) {
      const uint32_t fb = bars + 8 * (B_FX + q);
      mbar_expect_tx(fb, U + 8192);
      tma3d(sb + q * U, &maps.x, fb, 64 * q, 0, 2 * rb);
      if (q >= 4) mbar_wait(bars + 8 * (B_FE + ((q - 4) >> 1)), 0);
      tma2d(sb + OFF_XB + (q & 3) * 8192, &maps.ft, fb, 64 * q, 64 * j);
    };
    if (elect_one()) {
      if (warp == 14) {
#pragma unroll
        for (int i = 0; i < B_FT; i++) mbar_init(bars + 8 * i, 1);
        asm volatile("fence.proxy.async.shared::cta;" ::: "memory");
        if (!helper) {
#pragma unroll 1
          for (int n = 0; n < 2; n++) {
            const uint32_t fb = bars + 8 * (B_FA + n);
            xf_load(2 * n); xf_load(2 * n + 1);
            mbar_expect_tx(fb, U);
            tma2d(sb + OFF_RING + n * U, &maps.g64, fb, f_full, 64 * n);
            tma2d(sb + OFF_RING + n * U + 8192, &maps.u64, fb, f_full, 64 * n);
          }
        }
      } else if (warp == 15) {
#pragma unroll
        for (int i = B_FT; i < NBAR; i++) mbar_init(bars + 8 * i, i < B_EA ? 1 : i < B_T ? 2 : 4);
#pragma unroll
        for (int i = 0; i < 4; i++) mbar_expect_tx(bars + 8 * (B_Z + i), U);
        asm volatile("fence.mbarrier_init.release.cluster;" ::: "memory");
        asm volatile("fence.proxy.async.shared::cta;" ::: "memory");
      } else if (warp == 13) {
#pragma unroll
        for (int i = 1; i < 4; i++) asm volatile("prefetch.tensormap [%0];" ::"l"((const char*)&maps + i * 128) : "memory");
      }
    }
    __syncwarp();
    asm volatile("bar.arrive 0, 384;" ::: "memory");
    asm volatile("bar.arrive 4, 256;" ::: "memory");
    __syncwarp();
    asm volatile("barrier.cluster.arrive.relaxed.aligned;" ::: "memory");
    asm volatile("bar.sync 3, 128;" ::: "memory");
    if (warp == 15 && !helper) {
        mbar_wait(bars + 8 * B_FE, 0);
        const uint32_t tag = (ld_x1(&g_epoch[blockIdx.x * 8]) + 1) & 1;
        const int c = lane >> 4, jj = 16 * blockIdx.x + (lane & 15), jm = (2048 - jj) & 2047;
        const unsigned short* pr = (const unsigned short*)w_r + 256 * c;
        const unsigned short* pi = (const unsigned short*)w_i + 256 * c;
        const float wr = 0.25f * (bf_lo(__ldg(pr + jj * 257)) + bf_lo(__ldg(pr + jm * 257)));
        const float wi = 0.25f * (bf_lo(__ldg(pi + jj * 257)) - bf_lo(__ldg(pi + jm * 257)));
        st_u2(g_Wh + c * 2048 + jj, c ? pack_bf16(-wi, wr) : pack_bf16(wr, wi), tag);
        __syncwarp();
        hint_add_if(lane == 0, &g_cntW[0]);
      }
    if ((!helper || warp == 15) && elect_one()) {
      if (warp < 14) {
        const int p = warp - 12;
#pragma unroll 1
        for (int n = 2; n < 31; n++) {
          const bool table = n == 4 || n >= 29;
          const int q = n < 4 ? n : n - 1;
          const CUtensorMap* m = table ? &maps.e : n >= 25 ? &maps.g32 + p : &maps.g64 + p;
          const int c0 = table ? 0 : n >= 25 ? f_half : f_full + 64 * (q >> 3);
          const int c1 = table ? (2 * rb + ((n & 1) ^ 1)) * 128 + 64 * p : n >= 25 ? 128 * (n - 25) : 64 * (q & 7);
          const uint32_t fb = bars + 8 * (B_FA + (n & 3)), dst = sb + OFF_RING + (n & 3) * U + p * 8192;
          if (n < 4) mbar_wait(bars + 8 * (B_FE + n - 2), 0);
          else mbar_wait(bars + 8 * (B_EA + (n & 3)), ((n >> 2) & 1) ^ 1);
          tma2d(dst, m, fb, c0, c1);
          if (p == 0) mbar_expect_tx(fb, U);
        }
      } else if (warp == 15) {
        const unsigned ep1 = ld_x1(&g_epoch[blockIdx.x * 8]) + 1;
        flag_wait(&g_cntX[helper ? 0 : 32 * j], ep1 * 16u);
        PROF_EV(22);
        mbar_expect_tx(bars + 8 * B_HX, U);
        bulk_load(sb + OFF_XB, g_X + (size_t)(helper ? 128 : kg * 8 + tn) * 8192, U, bars + 8 * B_HX);
        if (!helper) {
          flag_wait(&g_cntT[32 * j], ep1 * 64u);
          PROF_EV(23);
          mbar_expect_tx(bars + 8 * B_TL, U);
          tma3d(sb + OFF_T, &maps.t, bars + 8 * B_TL, 64 * j, 0, 2 * rb);
#pragma unroll 1
          for (int i = 0; i < 3; i++) {
            mbar_wait(bars + 8 * (B_PZ + (i >> 1)), 0);
            flag_wait(&g_cntP[32 * (rb * 8 + j) + i], ep1 * 8u);
            if (i == 2) PROF_EV(26);
            mbar_expect_tx(bars + 8 * (B_HP + i), U);
            bulk_load(sb + i * U, g_part + (size_t)((rb * 8 + j) * 3 + i) * 1024, U, bars + 8 * (B_HP + i));
          }
          g_epoch[blockIdx.x * 8] = ep1;
        }
      } else {
#pragma unroll 1
        for (int q = 4; q < 8; q++) xf_load(q);
        mbar_wait(bars + 8 * (B_FE + 2), 0);
        mbar_expect_tx(bars + 8 * B_E0, U);
        tma2d(sb + OFF_XB, &maps.e, bars + 8 * B_E0, 0, 2 * rb * 128);
        tma2d(sb + OFF_XB + 8192, &maps.e, bars + 8 * B_E0, 0, 2 * rb * 128 + 64);
#pragma unroll 1
        for (int h2 = 0; h2 < 2; h2++) {
          const int s0 = 2 * rb + h2, sg = (s0 & ~6) | ((s0 & 2) << 1) | ((s0 & 4) >> 1);
          mbar_wait(bars + 8 * (B_XS + h2), 0);
#pragma unroll 1
          for (int c = 0; c < 2; c++) {
            asm volatile("cp.async.bulk.tensor.4d.global.shared::cta.bulk_group [%0, {%2, %3, %4, %5}], [%1];" ::"l"(&maps.xs),
                         "r"(sb + OFF_XB + h2 * 8192 + c * 4096), "r"(0), "r"(sg), "r"(0), "r"(16 * j + 8 * c) : "memory");
            if (j == 0)
              asm volatile("cp.async.bulk.global.shared::cta.bulk_group [%0], [%1], 256;" ::"l"(g_X + 128 * 8192 + c * 4096 + sg * 128),
                           "r"(sb + OFF_SP + h2 * 512 + c * 256) : "memory");
            if (SPACE && h2 + c < 2) __nanosleep(SPACE);
          }
        }
        bulk_done_signal(&g_cntX[32 * j]);
        PROF_EV(20);
#pragma unroll 1
        for (int t = 0; t < 8; t++) {
          const int i = t < 3 ? t + 1 : t < 6 ? t - 2 : 0;
          const int col = 64 * (2 * ((q4 + i) & 3) + ((t < 3 || t == 6) ? 1 - rank : rank));
          const uint32_t fb = bars + 8 * (B_FT + (t & 3)), dst = sb + (t & 3) * TB;
          mbar_wait(bars + 8 * (B_ET + (t == 2 ? 3 : t & 3)), t >> 2);
          mbar_expect_tx(fb, TB);
          tma2d(dst, &maps.d224, fb, col, 224 * j);
          if (t < 2) mbar_wait(bars + 8 * (B_ET + t + 1), 0);
          tma2d(dst + 28672, &maps.ft, fb, col, 64 * j);
        }
      }
    }
  }
}

typedef CUresult (*EncodeFn)(CUtensorMap*, CUtensorMapDataType, cuuint32_t, void*, const cuuint64_t*, const cuuint64_t*, const cuuint32_t*,
                             const cuuint32_t*, CUtensorMapInterleave, CUtensorMapSwizzle, CUtensorMapL2promotion, CUtensorMapFloatOOBfill);

static void encode(EncodeFn f, CUtensorMap* m, const void* base, int rank, const cuuint64_t* dims, const cuuint64_t* strides, const cuuint32_t* box,
                   CUtensorMapSwizzle sw) {
  cuuint32_t es[5] = {1, 1, 1, 1, 1};
  f(m, CU_TENSOR_MAP_DATA_TYPE_BFLOAT16, rank, (void*)base, dims, strides, box, es, CU_TENSOR_MAP_INTERLEAVE_NONE, sw,
    CU_TENSOR_MAP_L2_PROMOTION_L2_128B, CU_TENSOR_MAP_FLOAT_OOB_FILL_NONE);
}

extern "C" void kernel_launch(void* const* d_in, const int* in_sizes, int n_in, void* d_out, int out_size) {
  (void)in_sizes; (void)n_in; (void)out_size;
  const __nv_bfloat16* x = (const __nv_bfloat16*)d_in[0];
  const __nv_bfloat16* w_r = (const __nv_bfloat16*)d_in[1];
  const __nv_bfloat16* w_i = (const __nv_bfloat16*)d_in[2];
  const __nv_bfloat16* Wg = (const __nv_bfloat16*)d_in[4];
  const __nv_bfloat16* Wu = (const __nv_bfloat16*)d_in[5];
  const __nv_bfloat16* Wd = (const __nv_bfloat16*)d_in[6];
  const __nv_bfloat16* gw = (const __nv_bfloat16*)d_in[7];

  void* fp = nullptr; cudaDriverEntryPointQueryResult qr;
  cudaGetDriverEntryPoint("cuTensorMapEncodeTiled", &fp, cudaEnableDefault, &qr);
  EncodeFn enc = (EncodeFn)fp;
  void *pFT, *pET, *pX, *pT;
  cudaGetSymbolAddress(&pX, g_X); cudaGetSymbolAddress(&pT, g_T);
  cudaGetSymbolAddress(&pFT, g_FT); cudaGetSymbolAddress(&pET, g_ET);

  Maps mp;
  const CUtensorMapSwizzle S128 = CU_TENSOR_MAP_SWIZZLE_128B, S64 = CU_TENSOR_MAP_SWIZZLE_64B;
  { cuuint64_t d[3] = {512, 64, 32}, s[2] = {32768, 1024}; cuuint32_t b[3] = {64, 64, 2}; encode(enc, &mp.x, x, 3, d, s, b, S128); }
  { cuuint64_t d[2] = {512, 512}, s[1] = {1024}; cuuint32_t b[2] = {64, 64}; encode(enc, &mp.ft, pFT, 2, d, s, b, S128); }
  { cuuint64_t d[4] = {128, 32, 2, 129}, s[3] = {256, 8192, 16384}; cuuint32_t b[4] = {128, 1, 2, 8}; encode(enc, &mp.xs, pX, 4, d, s, b, CU_TENSOR_MAP_SWIZZLE_NONE); }
  { cuuint64_t d[3] = {512, 32, 64}, s[2] = {65536, 1024}; cuuint32_t b[3] = {32, 32, 2}; encode(enc, &mp.ts, pT, 3, d, s, b, S64); }
  { cuuint64_t d[3] = {512, 64, 32}, s[2] = {1024, 65536}; cuuint32_t b[3] = {64, 64, 2}; encode(enc, &mp.t, pT, 3, d, s, b, S128); }
  { cuuint64_t d[2] = {64, 4096}, s[1] = {128}; cuuint32_t b[2] = {64, 64}; encode(enc, &mp.e, pET, 2, d, s, b, S128); }
  { cuuint64_t d[2] = {1792, 512}, s[1] = {3584}; cuuint32_t b[2] = {64, 64}, b2[2] = {32, 128};
    encode(enc, &mp.g64, Wg, 2, d, s, b, S128); encode(enc, &mp.u64, Wu, 2, d, s, b, S128);
    encode(enc, &mp.g32, Wg, 2, d, s, b2, S64); encode(enc, &mp.u32, Wu, 2, d, s, b2, S64); }
  { cuuint64_t d[2] = {512, 1792}, s[1] = {1024}; cuuint32_t b[2] = {64, 224}; encode(enc, &mp.d224, Wd, 2, d, s, b, S128); }
  { cuuint64_t d[4] = {264, 32, 8, 8}, s[3] = {32896, 512, 4112}; cuuint32_t b[4] = {24, 32, 2, 1};
    encode(enc, &mp.wr, w_r, 4, d, s, b, CU_TENSOR_MAP_SWIZZLE_NONE); encode(enc, &mp.wi, w_i, 4, d, s, b, CU_TENSOR_MAP_SWIZZLE_NONE); }

  cudaFuncSetAttribute(fused_kernel, cudaFuncAttributeMaxDynamicSharedMemorySize, SMEM_BYTES);
  fused_kernel<<<NCTA, 512, SMEM_BYTES>>>(mp, w_r, w_i, gw, (__nv_bfloat16*)d_out);
}
```

```cpp
#include <cuda_runtime.h>
#include <cuda_bf16.h>
#include <cuda.h>
#include <stdint.h>

namespace tbl {
constexpr double PI = 3.14159265358979323846264338327950288;
constexpr double sin_s(double x) { double t = x, s = x; for (int n = 1; n < 12; n++) { t *= -x * x / ((2 * n) * (2 * n + 1)); s += t; } return s; }
constexpr double cos_s(double x) { double t = 1, s = 1; for (int n = 1; n < 12; n++) { t *= -x * x / ((2 * n - 1) * (2 * n)); s += t; } return s; }
constexpr double cos2048(int m) {
  m &= 2047; if (m > 1024) m = 2048 - m;
  bool neg = false; if (m > 512) { m = 1024 - m; neg = true; }
  double v = (m <= 256) ? cos_s(2 * PI * m / 2048) : sin_s(2 * PI * (512 - m) / 2048);
  return neg ? -v : v;
}
constexpr uint16_t to_bf16(double v) {
  if (v == 0) return 0;
  uint16_t s = 0; if (v < 0) { s = 0x8000; v = -v; }
  int e = 0; while (v >= 2) { v /= 2; e++; } while (v < 1) { v *= 2; e--; }
  double m = (v - 1) * 128; int mi = (int)m; double fr = m - mi;
  if (fr > 0.5 || (fr == 0.5 && (mi & 1))) mi++;
  if (mi == 128) { mi = 0; e++; }
  return (uint16_t)(s | ((e + 127) << 7) | mi);
}
struct CosT { uint16_t v[2048]; constexpr CosT() : v() { for (int i = 0; i < 2048; i++) v[i] = to_bf16(cos2048(i)); } };
struct alignas(1024) FT {
  uint16_t v[512 * 512];
  constexpr FT() : v() {
    CosT c;
    for (int r = 0; r < 512; r++) {
      int k = (r >> 4) * 8 + (r & 7), e = (r >> 3) & 1;
      int mul = 4 * k, add = e ? 512 : 0;
      if (k == 0 && e == 1) { mul = 1024; add = 0; }
      for (int d = 0; d < 512; d++) v[r * 512 + d] = c.v[(d * mul + add) & 2047];
    }
  }
};
struct alignas(1024) ET {
  uint16_t v[2048 * 128];
  constexpr ET() : v() {
    CosT c;
    for (int s = 0; s < 2048; s++)
      for (int j = 0; j < 64; j++) {
        const int o = (s & 31) * 8192 + (s >> 5) * 64 + j;
        v[o] = c.v[(s * j) & 2047]; v[o + 4096] = c.v[(s * j + 512) & 2047];
      }
  }
};
struct alignas(1024) DT {
  uint16_t v[64 * 64];
  constexpr DT() : v() {
    CosT c;
    for (int r = 0; r < 64; r++)
      for (int n = 0; n < 64; n++) {
        const int sg = r >> 1, s0 = (sg & ~6) | ((sg & 2) << 1) | ((sg & 4) >> 1), e = r & 1, f = n & 1;
        const int m = 64 * s0 * (n >> 1) + (e == f ? 0 : e ? -512 : 512);
        v[r * 64 + (((n >> 3) ^ (r & 7)) << 3) + (n & 7)] = c.v[m & 2047];
      }
  }
};
}

__device__ constexpr tbl::FT g_FT = tbl::FT();
__device__ constexpr tbl::ET g_ET = tbl::ET();
__device__ constexpr tbl::DT g_DT = tbl::DT();

__device__ __align__(1024) uint16_t g_X[129 * 8192];
__device__ __align__(1024) uint16_t g_T[32 * 64 * 512];
__device__ __align__(1024) uint2 g_Ts[32 * 64];
__device__ __align__(1024) uint4 g_part[128 * 3 * 1024];
__device__ __align__(16) float g_gate[16 * 128];
__device__ __align__(16) uint2 g_Wh[2 * 2048];
__device__ unsigned g_epoch[132 * 8];
__device__ unsigned g_cntX[8 * 32], g_cntT[8 * 32], g_cntP[128 * 32], g_cntW[32], g_cntH[32];
#define PROF_EV(i) do {} while (0)
#define PROF_CK(i) do {} while (0)

__device__ __forceinline__ uint32_t smem_u32(const void* p) { return (uint32_t)__cvta_generic_to_shared(p); }
__device__ __forceinline__ void mbar_init(uint32_t bar, uint32_t cnt) { asm volatile("mbarrier.init.shared::cta.b64 [%0], %1;" ::"r"(bar), "r"(cnt)); }
__device__ __forceinline__ void mbar_expect_tx(uint32_t bar, uint32_t bytes) { asm volatile("mbarrier.arrive.expect_tx.shared::cta.b64 _, [%0], %1;" ::"r"(bar), "r"(bytes) : "memory"); }
__device__ __forceinline__ void mbar_arrive(uint32_t bar) { asm volatile("mbarrier.arrive.shared::cta.b64 _, [%0];" ::"r"(bar) : "memory"); }
__device__ __forceinline__ bool elect_one() {
  uint32_t p;
  asm volatile("{\n.reg .pred p;\nelect.sync _|p, 0xffffffff;\nselp.u32 %0, 1, 0, p;\n}" : "=r"(p));
  return p;
}
__device__ __forceinline__ void mbar_arrive_if(bool p, uint32_t bar) {
  asm volatile("{\n.reg .pred p;\nsetp.ne.b32 p, %1, 0;\n@p mbarrier.arrive.shared::cta.b64 _, [%0];\n}" ::"r"(bar), "r"((int)p) : "memory");
}
__device__ __forceinline__ void hint_add_if(bool p, unsigned* a) {
  asm volatile("{\n.reg .pred p;\nsetp.ne.b32 p, %1, 0;\n@p red.relaxed.gpu.global.add.u32 [%0], 1;\n}" ::"l"(a), "r"((int)p) : "memory");
}
__device__ __forceinline__ bool mbar_try(uint32_t bar, uint32_t parity) {
  uint32_t ok;
  asm volatile("{\n.reg .pred p;\nmbarrier.test_wait.parity.shared::cta.b64 p, [%1], %2;\nselp.u32 %0, 1, 0, p;\n}" : "=r"(ok) : "r"(bar), "r"(parity) : "memory");
  return ok;
}
__device__ __forceinline__ void mbar_wait(uint32_t bar, uint32_t parity) {
  asm volatile(
      "{\n.reg .pred p;\n.reg .u32 n;\nmov.u32 n, 0;\n"
      "W_LOOP:\nmbarrier.try_wait.parity.shared::cta.b64 p, [%0], %1;\n@p bra W_DONE;\n"
      "add.u32 n, n, 1;\nsetp.lt.u32 p, n, 0x40000;\n@p bra W_LOOP;\ntrap;\nW_DONE:\n}" ::"r"(bar), "r"(parity) : "memory");
}
__device__ __forceinline__ void bulk_load(uint32_t dst, const void* src, uint32_t bytes, uint32_t bar) {
  asm volatile("cp.async.bulk.shared::cluster.global.mbarrier::complete_tx::bytes [%0], [%1], %2, [%3];" ::"r"(dst), "l"(src), "r"(bytes), "r"(bar) : "memory");
}
__device__ __forceinline__ void cp16(uint32_t dst, const void* src) { asm volatile("cp.async.cg.shared.global [%0], [%1], 16;" ::"r"(dst), "l"(src) : "memory"); }
__device__ __forceinline__ void spin_guard(uint32_t t0) { if ((uint32_t)clock() - t0 > (1u << 30)) __trap(); }
__device__ __forceinline__ float tagf(float v, uint32_t tag) { return __uint_as_float((__float_as_uint(v) & ~1u) | tag); }
__device__ __forceinline__ float untag(float v) { return __uint_as_float(__float_as_uint(v) & ~1u); }
__device__ __forceinline__ void st_x2(float2* p, float a, float b) { asm volatile("st.relaxed.gpu.global.v2.f32 [%0], {%1,%2};" ::"l"(p), "f"(a), "f"(b) : "memory"); }
__device__ __forceinline__ float2 ld_x2(const float2* p) { float2 v; asm volatile("ld.relaxed.gpu.global.v2.f32 {%0,%1}, [%2];" : "=f"(v.x), "=f"(v.y) : "l"(p) : "memory"); return v; }
__device__ __forceinline__ void st_u2(uint2* p, uint32_t a, uint32_t b) { asm volatile("st.relaxed.gpu.global.v2.u32 [%0], {%1,%2};" ::"l"(p), "r"(a), "r"(b) : "memory"); }
__device__ __forceinline__ void prefetch2d(const CUtensorMap* m, int c0, int c1) { asm volatile("cp.async.bulk.prefetch.tensor.2d.L2.global [%0, {%1, %2}];" ::"l"(m), "r"(c0), "r"(c1) : "memory"); }
__device__ __forceinline__ void prefetch1d(const void* p, uint32_t bytes) { asm volatile("cp.async.bulk.prefetch.L2.global [%0], %1;" ::"l"(p), "r"(bytes) : "memory"); }
__device__ __forceinline__ uint32_t ld_x1(const void* p) { uint32_t v; asm volatile("ld.relaxed.gpu.global.u32 %0, [%1];" : "=r"(v) : "l"(p) : "memory"); return v; }
__device__ __forceinline__ uint4 ld_x4(const void* p) { uint4 v; asm volatile("ld.relaxed.gpu.global.v4.u32 {%0,%1,%2,%3}, [%4];" : "=r"(v.x), "=r"(v.y), "=r"(v.z), "=r"(v.w) : "l"(p) : "memory"); return v; }
__device__ __forceinline__ void st_x4(void* p, uint32_t a, uint32_t b, uint32_t c, uint32_t d) { asm volatile("st.relaxed.gpu.global.v4.u32 [%0], {%1,%2,%3,%4};" ::"l"(p), "r"(a), "r"(b), "r"(c), "r"(d) : "memory"); }
__device__ __forceinline__ uint32_t mapa(uint32_t a, uint32_t cta) { uint32_t r; asm volatile("mapa.shared::cluster.u32 %0, %1, %2;" : "=r"(r) : "r"(a), "r"(cta)); return r; }
__device__ __forceinline__ void stsm4t(uint32_t a, uint32_t r0, uint32_t r1, uint32_t r2, uint32_t r3) {
  asm volatile("stmatrix.sync.aligned.m8n8.x4.trans.shared.b16 [%0], {%1,%2,%3,%4};" ::"r"(a), "r"(r0), "r"(r1), "r"(r2), "r"(r3) : "memory");
}
__device__ __forceinline__ void hint_add(unsigned* p) { asm volatile("red.relaxed.gpu.global.add.u32 [%0], 1;" ::"l"(p) : "memory"); }
__device__ __forceinline__ void hint_wait(const unsigned* p, unsigned target) {
  const uint32_t t0 = (uint32_t)clock();
  while ((int)(ld_x1(p) - target) < 0) spin_guard(t0);
}
__device__ __forceinline__ void bulk_done_signal(unsigned* p) {
  asm volatile("cp.async.bulk.commit_group;\ncp.async.bulk.wait_group 0;\nfence.proxy.async.global;" ::: "memory");
  hint_add(p);
}
__device__ __forceinline__ void flag_wait(const unsigned* p, unsigned target) {
  hint_wait(p, target);
  asm volatile("fence.proxy.async.global;" ::: "memory");
}
__device__ __forceinline__ void tma2d(uint32_t dst, const CUtensorMap* m, uint32_t bar, int c0, int c1) {
  asm volatile("cp.async.bulk.tensor.2d.shared::cluster.global.mbarrier::complete_tx::bytes [%0], [%1, {%3, %4}], [%2];" ::"r"(dst), "l"(m), "r"(bar), "r"(c0), "r"(c1) : "memory");
}
__device__ __forceinline__ void tma3d(uint32_t dst, const CUtensorMap* m, uint32_t bar, int c0, int c1, int c2) {
  asm volatile("cp.async.bulk.tensor.3d.shared::cluster.global.mbarrier::complete_tx::bytes [%0], [%1, {%3, %4, %5}], [%2];" ::"r"(dst), "l"(m), "r"(bar), "r"(c0), "r"(c1), "r"(c2) : "memory");
}
__device__ __forceinline__ void tma4d(uint32_t dst, const CUtensorMap* m, uint32_t bar, int c0, int c1, int c2, int c3) {
  asm volatile("cp.async.bulk.tensor.4d.shared::cluster.global.mbarrier::complete_tx::bytes [%0], [%1, {%3, %4, %5, %6}], [%2];" ::"r"(dst), "l"(m), "r"(bar), "r"(c0), "r"(c1), "r"(c2), "r"(c3) : "memory");
}
__device__ __forceinline__ void wg_fence() { asm volatile("wgmma.fence.sync.aligned;" ::: "memory"); }
__device__ __forceinline__ void wg_commit() { asm volatile("wgmma.commit_group.sync.aligned;" ::: "memory"); }
template <int N> __device__ __forceinline__ void wg_wait() { asm volatile("wgmma.wait_group.sync.aligned %0;" ::"n"(N) : "memory"); }
template <int O, int N, int NN> __device__ __forceinline__ void fence_regs(float (&d)[NN]) {
#pragma unroll
  for (int i = 0; i < N; i++) asm volatile("" : "+f"(d[O + i])::"memory");
}
__device__ __forceinline__ uint32_t pack_bf16(float lo, float hi) {
  uint32_t r; asm("cvt.rn.bf16x2.f32 %0, %1, %2;" : "=r"(r) : "f"(hi), "f"(lo)); return r;
}
__device__ __forceinline__ uint32_t pack_pin(float lo, float hi) {
  uint32_t r; asm volatile("cvt.rn.bf16x2.f32 %0, %1, %2;" : "=r"(r) : "f"(hi), "f"(lo) : "memory"); return r;
}
__device__ __forceinline__ float bf_lo(uint32_t u) { return __uint_as_float(u << 16); }
__device__ __forceinline__ float bf_hi(uint32_t u) { return __uint_as_float(u & 0xffff0000u); }

__device__ __forceinline__ uint64_t d128(uint32_t lo) { uint64_t d; asm("mov.b64 %0, {%1, 0x40000040};" : "=l"(d) : "r"(lo)); return d; }
__device__ __forceinline__ uint64_t d64(uint32_t lo) { uint64_t d; asm("mov.b64 %0, {%1, 0x80000020};" : "=l"(d) : "r"(lo)); return d; }
template<int O,int TB,int ACC,int NN> __device__ __forceinline__ void mma_ss64(float (&d)[NN], uint64_t da, uint64_t db, int sd = 0){
  if constexpr (ACC == 1) asm volatile("wgmma.mma_async.sync.aligned.m64n64k16.f32.bf16.bf16 {%0,%1,%2,%3,%4,%5,%6,%7,%8,%9,%10,%11,%12,%13,%14,%15,%16,%17,%18,%19,%20,%21,%22,%23,%24,%25,%26,%27,%28,%29,%30,%31}, %32, %33, 1, 1, 1, %35, %34;"
   : "+f"(d[O+0]), "+f"(d[O+1]), "+f"(d[O+2]), "+f"(d[O+3]), "+f"(d[O+4]), "+f"(d[O+5]), "+f"(d[O+6]), "+f"(d[O+7]), "+f"(d[O+8]), "+f"(d[O+9]), "+f"(d[O+10]), "+f"(d[O+11]), "+f"(d[O+12]), "+f"(d[O+13]), "+f"(d[O+14]), "+f"(d[O+15]), "+f"(d[O+16]), "+f"(d[O+17]), "+f"(d[O+18]), "+f"(d[O+19]), "+f"(d[O+20]), "+f"(d[O+21]), "+f"(d[O+22]), "+f"(d[O+23]), "+f"(d[O+24]), "+f"(d[O+25]), "+f"(d[O+26]), "+f"(d[O+27]), "+f"(d[O+28]), "+f"(d[O+29]), "+f"(d[O+30]), "+f"(d[O+31])
   : "l"(da), "l"(db), "n"(TB & 1), "n"(TB >> 1));
  else if constexpr (ACC == 0) asm volatile("wgmma.mma_async.sync.aligned.m64n64k16.f32.bf16.bf16 {%0,%1,%2,%3,%4,%5,%6,%7,%8,%9,%10,%11,%12,%13,%14,%15,%16,%17,%18,%19,%20,%21,%22,%23,%24,%25,%26,%27,%28,%29,%30,%31}, %32, %33, 0, 1, 1, %35, %34;"
   : "=f"(d[O+0]), "=f"(d[O+1]), "=f"(d[O+2]), "=f"(d[O+3]), "=f"(d[O+4]), "=f"(d[O+5]), "=f"(d[O+6]), "=f"(d[O+7]), "=f"(d[O+8]), "=f"(d[O+9]), "=f"(d[O+10]), "=f"(d[O+11]), "=f"(d[O+12]), "=f"(d[O+13]), "=f"(d[O+14]), "=f"(d[O+15]), "=f"(d[O+16]), "=f"(d[O+17]), "=f"(d[O+18]), "=f"(d[O+19]), "=f"(d[O+20]), "=f"(d[O+21]), "=f"(d[O+22]), "=f"(d[O+23]), "=f"(d[O+24]), "=f"(d[O+25]), "=f"(d[O+26]), "=f"(d[O+27]), "=f"(d[O+28]), "=f"(d[O+29]), "=f"(d[O+30]), "=f"(d[O+31])
   : "l"(da), "l"(db), "n"(TB & 1), "n"(TB >> 1));
  else asm volatile("{\n.reg .pred p;\nsetp.ne.b32 p, %36, 0;\nwgmma.mma_async.sync.aligned.m64n64k16.f32.bf16.bf16 {%0,%1,%2,%3,%4,%5,%6,%7,%8,%9,%10,%11,%12,%13,%14,%15,%16,%17,%18,%19,%20,%21,%22,%23,%24,%25,%26,%27,%28,%29,%30,%31}, %32, %33, p, 1, 1, %35, %34;\n}"
   : "+f"(d[O+0]), "+f"(d[O+1]), "+f"(d[O+2]), "+f"(d[O+3]), "+f"(d[O+4]), "+f"(d[O+5]), "+f"(d[O+6]), "+f"(d[O+7]), "+f"(d[O+8]), "+f"(d[O+9]), "+f"(d[O+10]), "+f"(d[O+11]), "+f"(d[O+12]), "+f"(d[O+13]), "+f"(d[O+14]), "+f"(d[O+15]), "+f"(d[O+16]), "+f"(d[O+17]), "+f"(d[O+18]), "+f"(d[O+19]), "+f"(d[O+20]), "+f"(d[O+21]), "+f"(d[O+22]), "+f"(d[O+23]), "+f"(d[O+24]), "+f"(d[O+25]), "+f"(d[O+26]), "+f"(d[O+27]), "+f"(d[O+28]), "+f"(d[O+29]), "+f"(d[O+30]), "+f"(d[O+31])
   : "l"(da), "l"(db), "n"(TB & 1), "n"(TB >> 1), "r"(sd));
}
template<int O,int TB,int ACC,int NN> __device__ __forceinline__ void mma_rs64(float (&d)[NN], uint32_t a0, uint32_t a1, uint32_t a2, uint32_t a3, uint64_t db, int sd = 0){
  if constexpr (ACC == 1) asm volatile("wgmma.mma_async.sync.aligned.m64n64k16.f32.bf16.bf16 {%0,%1,%2,%3,%4,%5,%6,%7,%8,%9,%10,%11,%12,%13,%14,%15,%16,%17,%18,%19,%20,%21,%22,%23,%24,%25,%26,%27,%28,%29,%30,%31}, {%32,%33,%34,%35}, %36, 1, 1, 1, %37;"
   : "+f"(d[O+0]), "+f"(d[O+1]), "+f"(d[O+2]), "+f"(d[O+3]), "+f"(d[O+4]), "+f"(d[O+5]), "+f"(d[O+6]), "+f"(d[O+7]), "+f"(d[O+8]), "+f"(d[O+9]), "+f"(d[O+10]), "+f"(d[O+11]), "+f"(d[O+12]), "+f"(d[O+13]), "+f"(d[O+14]), "+f"(d[O+15]), "+f"(d[O+16]), "+f"(d[O+17]), "+f"(d[O+18]), "+f"(d[O+19]), "+f"(d[O+20]), "+f"(d[O+21]), "+f"(d[O+22]), "+f"(d[O+23]), "+f"(d[O+24]), "+f"(d[O+25]), "+f"(d[O+26]), "+f"(d[O+27]), "+f"(d[O+28]), "+f"(d[O+29]), "+f"(d[O+30]), "+f"(d[O+31])
   : "r"(a0), "r"(a1), "r"(a2), "r"(a3), "l"(db), "n"(TB));
  else if constexpr (ACC == 0) asm volatile("wgmma.mma_async.sync.aligned.m64n64k16.f32.bf16.bf16 {%0,%1,%2,%3,%4,%5,%6,%7,%8,%9,%10,%11,%12,%13,%14,%15,%16,%17,%18,%19,%20,%21,%22,%23,%24,%25,%26,%27,%28,%29,%30,%31}, {%32,%33,%34,%35}, %36, 0, 1, 1, %37;"
   : "=f"(d[O+0]), "=f"(d[O+1]), "=f"(d[O+2]), "=f"(d[O+3]), "=f"(d[O+4]), "=f"(d[O+5]), "=f"(d[O+6]), "=f"(d[O+7]), "=f"(d[O+8]), "=f"(d[O+9]), "=f"(d[O+10]), "=f"(d[O+11]), "=f"(d[O+12]), "=f"(d[O+13]), "=f"(d[O+14]), "=f"(d[O+15]), "=f"(d[O+16]), "=f"(d[O+17]), "=f"(d[O+18]), "=f"(d[O+19]), "=f"(d[O+20]), "=f"(d[O+21]), "=f"(d[O+22]), "=f"(d[O+23]), "=f"(d[O+24]), "=f"(d[O+25]), "=f"(d[O+26]), "=f"(d[O+27]), "=f"(d[O+28]), "=f"(d[O+29]), "=f"(d[O+30]), "=f"(d[O+31])
   : "r"(a0), "r"(a1), "r"(a2), "r"(a3), "l"(db), "n"(TB));
  else asm volatile("{\n.reg .pred p;\nsetp.ne.b32 p, %38, 0;\nwgmma.mma_async.sync.aligned.m64n64k16.f32.bf16.bf16 {%0,%1,%2,%3,%4,%5,%6,%7,%8,%9,%10,%11,%12,%13,%14,%15,%16,%17,%18,%19,%20,%21,%22,%23,%24,%25,%26,%27,%28,%29,%30,%31}, {%32,%33,%34,%35}, %36, p, 1, 1, %37;\n}"
   : "+f"(d[O+0]), "+f"(d[O+1]), "+f"(d[O+2]), "+f"(d[O+3]), "+f"(d[O+4]), "+f"(d[O+5]), "+f"(d[O+6]), "+f"(d[O+7]), "+f"(d[O+8]), "+f"(d[O+9]), "+f"(d[O+10]), "+f"(d[O+11]), "+f"(d[O+12]), "+f"(d[O+13]), "+f"(d[O+14]), "+f"(d[O+15]), "+f"(d[O+16]), "+f"(d[O+17]), "+f"(d[O+18]), "+f"(d[O+19]), "+f"(d[O+20]), "+f"(d[O+21]), "+f"(d[O+22]), "+f"(d[O+23]), "+f"(d[O+24]), "+f"(d[O+25]), "+f"(d[O+26]), "+f"(d[O+27]), "+f"(d[O+28]), "+f"(d[O+29]), "+f"(d[O+30]), "+f"(d[O+31])
   : "r"(a0), "r"(a1), "r"(a2), "r"(a3), "l"(db), "n"(TB), "r"(sd));
}
template<int O,int TB,int ACC,int NN> __device__ __forceinline__ void mma_ss128(float (&d)[NN], uint64_t da, uint64_t db, int sd = 0){
  if constexpr (ACC == 1) asm volatile("wgmma.mma_async.sync.aligned.m64n128k16.f32.bf16.bf16 {%0,%1,%2,%3,%4,%5,%6,%7,%8,%9,%10,%11,%12,%13,%14,%15,%16,%17,%18,%19,%20,%21,%22,%23,%24,%25,%26,%27,%28,%29,%30,%31,%32,%33,%34,%35,%36,%37,%38,%39,%40,%41,%42,%43,%44,%45,%46,%47,%48,%49,%50,%51,%52,%53,%54,%55,%56,%57,%58,%59,%60,%61,%62,%63}, %64, %65, 1, 1, 1, %67, %66;"
   : "+f"(d[O+0]), "+f"(d[O+1]), "+f"(d[O+2]), "+f"(d[O+3]), "+f"(d[O+4]), "+f"(d[O+5]), "+f"(d[O+6]), "+f"(d[O+7]), "+f"(d[O+8]), "+f"(d[O+9]), "+f"(d[O+10]), "+f"(d[O+11]), "+f"(d[O+12]), "+f"(d[O+13]), "+f"(d[O+14]), "+f"(d[O+15]), "+f"(d[O+16]), "+f"(d[O+17]), "+f"(d[O+18]), "+f"(d[O+19]), "+f"(d[O+20]), "+f"(d[O+21]), "+f"(d[O+22]), "+f"(d[O+23]), "+f"(d[O+24]), "+f"(d[O+25]), "+f"(d[O+26]), "+f"(d[O+27]), "+f"(d[O+28]), "+f"(d[O+29]), "+f"(d[O+30]), "+f"(d[O+31]), "+f"(d[O+32]), "+f"(d[O+33]), "+f"(d[O+34]), "+f"(d[O+35]), "+f"(d[O+36]), "+f"(d[O+37]), "+f"(d[O+38]), "+f"(d[O+39]), "+f"(d[O+40]), "+f"(d[O+41]), "+f"(d[O+42]), "+f"(d[O+43]), "+f"(d[O+44]), "+f"(d[O+45]), "+f"(d[O+46]), "+f"(d[O+47]), "+f"(d[O+48]), "+f"(d[O+49]), "+f"(d[O+50]), "+f"(d[O+51]), "+f"(d[O+52]), "+f"(d[O+53]), "+f"(d[O+54]), "+f"(d[O+55]), "+f"(d[O+56]), "+f"(d[O+57]), "+f"(d[O+58]), "+f"(d[O+59]), "+f"(d[O+60]), "+f"(d[O+61]), "+f"(d[O+62]), "+f"(d[O+63])
   : "l"(da), "l"(db), "n"(TB & 1), "n"(TB >> 1));
  else if constexpr (ACC == 0) asm volatile("wgmma.mma_async.sync.aligned.m64n128k16.f32.bf16.bf16 {%0,%1,%2,%3,%4,%5,%6,%7,%8,%9,%10,%11,%12,%13,%14,%15,%16,%17,%18,%19,%20,%21,%22,%23,%24,%25,%26,%27,%28,%29,%30,%31,%32,%33,%34,%35,%36,%37,%38,%39,%40,%41,%42,%43,%44,%45,%46,%47,%48,%49,%50,%51,%52,%53,%54,%55,%56,%57,%58,%59,%60,%61,%62,%63}, %64, %65, 0, 1, 1, %67, %66;"
   : "=f"(d[O+0]), "=f"(d[O+1]), "=f"(d[O+2]), "=f"(d[O+3]), "=f"(d[O+4]), "=f"(d[O+5]), "=f"(d[O+6]), "=f"(d[O+7]), "=f"(d[O+8]), "=f"(d[O+9]), "=f"(d[O+10]), "=f"(d[O+11]), "=f"(d[O+12]), "=f"(d[O+13]), "=f"(d[O+14]), "=f"(d[O+15]), "=f"(d[O+16]), "=f"(d[O+17]), "=f"(d[O+18]), "=f"(d[O+19]), "=f"(d[O+20]), "=f"(d[O+21]), "=f"(d[O+22]), "=f"(d[O+23]), "=f"(d[O+24]), "=f"(d[O+25]), "=f"(d[O+26]), "=f"(d[O+27]), "=f"(d[O+28]), "=f"(d[O+29]), "=f"(d[O+30]), "=f"(d[O+31]), "=f"(d[O+32]), "=f"(d[O+33]), "=f"(d[O+34]), "=f"(d[O+35]), "=f"(d[O+36]), "=f"(d[O+37]), "=f"(d[O+38]), "=f"(d[O+39]), "=f"(d[O+40]), "=f"(d[O+41]), "=f"(d[O+42]), "=f"(d[O+43]), "=f"(d[O+44]), "=f"(d[O+45]), "=f"(d[O+46]), "=f"(d[O+47]), "=f"(d[O+48]), "=f"(d[O+49]), "=f"(d[O+50]), "=f"(d[O+51]), "=f"(d[O+52]), "=f"(d[O+53]), "=f"(d[O+54]), "=f"(d[O+55]), "=f"(d[O+56]), "=f"(d[O+57]), "=f"(d[O+58]), "=f"(d[O+59]), "=f"(d[O+60]), "=f"(d[O+61]), "=f"(d[O+62]), "=f"(d[O+63])
   : "l"(da), "l"(db), "n"(TB & 1), "n"(TB >> 1));
  else asm volatile("{\n.reg .pred p;\nsetp.ne.b32 p, %68, 0;\nwgmma.mma_async.sync.aligned.m64n128k16.f32.bf16.bf16 {%0,%1,%2,%3,%4,%5,%6,%7,%8,%9,%10,%11,%12,%13,%14,%15,%16,%17,%18,%19,%20,%21,%22,%23,%24,%25,%26,%27,%28,%29,%30,%31,%32,%33,%34,%35,%36,%37,%38,%39,%40,%41,%42,%43,%44,%45,%46,%47,%48,%49,%50,%51,%52,%53,%54,%55,%56,%57,%58,%59,%60,%61,%62,%63}, %64, %65, p, 1, 1, %67, %66;\n}"
   : "+f"(d[O+0]), "+f"(d[O+1]), "+f"(d[O+2]), "+f"(d[O+3]), "+f"(d[O+4]), "+f"(d[O+5]), "+f"(d[O+6]), "+f"(d[O+7]), "+f"(d[O+8]), "+f"(d[O+9]), "+f"(d[O+10]), "+f"(d[O+11]), "+f"(d[O+12]), "+f"(d[O+13]), "+f"(d[O+14]), "+f"(d[O+15]), "+f"(d[O+16]), "+f"(d[O+17]), "+f"(d[O+18]), "+f"(d[O+19]), "+f"(d[O+20]), "+f"(d[O+21]), "+f"(d[O+22]), "+f"(d[O+23]), "+f"(d[O+24]), "+f"(d[O+25]), "+f"(d[O+26]), "+f"(d[O+27]), "+f"(d[O+28]), "+f"(d[O+29]), "+f"(d[O+30]), "+f"(d[O+31]), "+f"(d[O+32]), "+f"(d[O+33]), "+f"(d[O+34]), "+f"(d[O+35]), "+f"(d[O+36]), "+f"(d[O+37]), "+f"(d[O+38]), "+f"(d[O+39]), "+f"(d[O+40]), "+f"(d[O+41]), "+f"(d[O+42]), "+f"(d[O+43]), "+f"(d[O+44]), "+f"(d[O+45]), "+f"(d[O+46]), "+f"(d[O+47]), "+f"(d[O+48]), "+f"(d[O+49]), "+f"(d[O+50]), "+f"(d[O+51]), "+f"(d[O+52]), "+f"(d[O+53]), "+f"(d[O+54]), "+f"(d[O+55]), "+f"(d[O+56]), "+f"(d[O+57]), "+f"(d[O+58]), "+f"(d[O+59]), "+f"(d[O+60]), "+f"(d[O+61]), "+f"(d[O+62]), "+f"(d[O+63])
   : "l"(da), "l"(db), "n"(TB & 1), "n"(TB >> 1), "r"(sd));
}
template<int O,int TB,int ACC,int NN> __device__ __forceinline__ void mma_rs128(float (&d)[NN], uint32_t a0, uint32_t a1, uint32_t a2, uint32_t a3, uint64_t db, int sd = 0){
  if constexpr (ACC == 1) asm volatile("wgmma.mma_async.sync.aligned.m64n128k16.f32.bf16.bf16 {%0,%1,%2,%3,%4,%5,%6,%7,%8,%9,%10,%11,%12,%13,%14,%15,%16,%17,%18,%19,%20,%21,%22,%23,%24,%25,%26,%27,%28,%29,%30,%31,%32,%33,%34,%35,%36,%37,%38,%39,%40,%41,%42,%43,%44,%45,%46,%47,%48,%49,%50,%51,%52,%53,%54,%55,%56,%57,%58,%59,%60,%61,%62,%63}, {%64,%65,%66,%67}, %68, 1, 1, 1, %69;"
   : "+f"(d[O+0]), "+f"(d[O+1]), "+f"(d[O+2]), "+f"(d[O+3]), "+f"(d[O+4]), "+f"(d[O+5]), "+f"(d[O+6]), "+f"(d[O+7]), "+f"(d[O+8]), "+f"(d[O+9]), "+f"(d[O+10]), "+f"(d[O+11]), "+f"(d[O+12]), "+f"(d[O+13]), "+f"(d[O+14]), "+f"(d[O+15]), "+f"(d[O+16]), "+f"(d[O+17]), "+f"(d[O+18]), "+f"(d[O+19]), "+f"(d[O+20]), "+f"(d[O+21]), "+f"(d[O+22]), "+f"(d[O+23]), "+f"(d[O+24]), "+f"(d[O+25]), "+f"(d[O+26]), "+f"(d[O+27]), "+f"(d[O+28]), "+f"(d[O+29]), "+f"(d[O+30]), "+f"(d[O+31]), "+f"(d[O+32]), "+f"(d[O+33]), "+f"(d[O+34]), "+f"(d[O+35]), "+f"(d[O+36]), "+f"(d[O+37]), "+f"(d[O+38]), "+f"(d[O+39]), "+f"(d[O+40]), "+f"(d[O+41]), "+f"(d[O+42]), "+f"(d[O+43]), "+f"(d[O+44]), "+f"(d[O+45]), "+f"(d[O+46]), "+f"(d[O+47]), "+f"(d[O+48]), "+f"(d[O+49]), "+f"(d[O+50]), "+f"(d[O+51]), "+f"(d[O+52]), "+f"(d[O+53]), "+f"(d[O+54]), "+f"(d[O+55]), "+f"(d[O+56]), "+f"(d[O+57]), "+f"(d[O+58]), "+f"(d[O+59]), "+f"(d[O+60]), "+f"(d[O+61]), "+f"(d[O+62]), "+f"(d[O+63])
   : "r"(a0), "r"(a1), "r"(a2), "r"(a3), "l"(db), "n"(TB));
  else if constexpr (ACC == 0) asm volatile("wgmma.mma_async.sync.aligned.m64n128k16.f32.bf16.bf16 {%0,%1,%2,%3,%4,%5,%6,%7,%8,%9,%10,%11,%12,%13,%14,%15,%16,%17,%18,%19,%20,%21,%22,%23,%24,%25,%26,%27,%28,%29,%30,%31,%32,%33,%34,%35,%36,%37,%38,%39,%40,%41,%42,%43,%44,%45,%46,%47,%48,%49,%50,%51,%52,%53,%54,%55,%56,%57,%58,%59,%60,%61,%62,%63}, {%64,%65,%66,%67}, %68, 0, 1, 1, %69;"
   : "=f"(d[O+0]), "=f"(d[O+1]), "=f"(d[O+2]), "=f"(d[O+3]), "=f"(d[O+4]), "=f"(d[O+5]), "=f"(d[O+6]), "=f"(d[O+7]), "=f"(d[O+8]), "=f"(d[O+9]), "=f"(d[O+10]), "=f"(d[O+11]), "=f"(d[O+12]), "=f"(d[O+13]), "=f"(d[O+14]), "=f"(d[O+15]), "=f"(d[O+16]), "=f"(d[O+17]), "=f"(d[O+18]), "=f"(d[O+19]), "=f"(d[O+20]), "=f"(d[O+21]), "=f"(d[O+22]), "=f"(d[O+23]), "=f"(d[O+24]), "=f"(d[O+25]), "=f"(d[O+26]), "=f"(d[O+27]), "=f"(d[O+28]), "=f"(d[O+29]), "=f"(d[O+30]), "=f"(d[O+31]), "=f"(d[O+32]), "=f"(d[O+33]), "=f"(d[O+34]), "=f"(d[O+35]), "=f"(d[O+36]), "=f"(d[O+37]), "=f"(d[O+38]), "=f"(d[O+39]), "=f"(d[O+40]), "=f"(d[O+41]), "=f"(d[O+42]), "=f"(d[O+43]), "=f"(d[O+44]), "=f"(d[O+45]), "=f"(d[O+46]), "=f"(d[O+47]), "=f"(d[O+48]), "=f"(d[O+49]), "=f"(d[O+50]), "=f"(d[O+51]), "=f"(d[O+52]), "=f"(d[O+53]), "=f"(d[O+54]), "=f"(d[O+55]), "=f"(d[O+56]), "=f"(d[O+57]), "=f"(d[O+58]), "=f"(d[O+59]), "=f"(d[O+60]), "=f"(d[O+61]), "=f"(d[O+62]), "=f"(d[O+63])
   : "r"(a0), "r"(a1), "r"(a2), "r"(a3), "l"(db), "n"(TB));
  else asm volatile("{\n.reg .pred p;\nsetp.ne.b32 p, %70, 0;\nwgmma.mma_async.sync.aligned.m64n128k16.f32.bf16.bf16 {%0,%1,%2,%3,%4,%5,%6,%7,%8,%9,%10,%11,%12,%13,%14,%15,%16,%17,%18,%19,%20,%21,%22,%23,%24,%25,%26,%27,%28,%29,%30,%31,%32,%33,%34,%35,%36,%37,%38,%39,%40,%41,%42,%43,%44,%45,%46,%47,%48,%49,%50,%51,%52,%53,%54,%55,%56,%57,%58,%59,%60,%61,%62,%63}, {%64,%65,%66,%67}, %68, p, 1, 1, %69;\n}"
   : "+f"(d[O+0]), "+f"(d[O+1]), "+f"(d[O+2]), "+f"(d[O+3]), "+f"(d[O+4]), "+f"(d[O+5]), "+f"(d[O+6]), "+f"(d[O+7]), "+f"(d[O+8]), "+f"(d[O+9]), "+f"(d[O+10]), "+f"(d[O+11]), "+f"(d[O+12]), "+f"(d[O+13]), "+f"(d[O+14]), "+f"(d[O+15]), "+f"(d[O+16]), "+f"(d[O+17]), "+f"(d[O+18]), "+f"(d[O+19]), "+f"(d[O+20]), "+f"(d[O+21]), "+f"(d[O+22]), "+f"(d[O+23]), "+f"(d[O+24]), "+f"(d[O+25]), "+f"(d[O+26]), "+f"(d[O+27]), "+f"(d[O+28]), "+f"(d[O+29]), "+f"(d[O+30]), "+f"(d[O+31]), "+f"(d[O+32]), "+f"(d[O+33]), "+f"(d[O+34]), "+f"(d[O+35]), "+f"(d[O+36]), "+f"(d[O+37]), "+f"(d[O+38]), "+f"(d[O+39]), "+f"(d[O+40]), "+f"(d[O+41]), "+f"(d[O+42]), "+f"(d[O+43]), "+f"(d[O+44]), "+f"(d[O+45]), "+f"(d[O+46]), "+f"(d[O+47]), "+f"(d[O+48]), "+f"(d[O+49]), "+f"(d[O+50]), "+f"(d[O+51]), "+f"(d[O+52]), "+f"(d[O+53]), "+f"(d[O+54]), "+f"(d[O+55]), "+f"(d[O+56]), "+f"(d[O+57]), "+f"(d[O+58]), "+f"(d[O+59]), "+f"(d[O+60]), "+f"(d[O+61]), "+f"(d[O+62]), "+f"(d[O+63])
   : "r"(a0), "r"(a1), "r"(a2), "r"(a3), "l"(db), "n"(TB), "r"(sd));
}

#define NEARLY 0
#define XAHEAD 3
#define HEADN 6
#define WBATCH 1
#define NOLDS 2
#define SPACE 0
#define WPF 1
#define WAFTER 7
#define WPACE 0
#define GATE_AT 4
#define TPACE 40
#define PFMODE 0
#define MAPMODE 0
template <int V> struct IC { static constexpr int value = V; };
struct Maps { CUtensorMap x, ft, g64, u64, e, wr, wi, xs, ts, t, g32, u32, d224; };

constexpr int NCTA = 130;
constexpr int U = 16384;
constexpr int TB = 36864;
constexpr int OFF_RING = 8 * U, OFF_Z = 9 * U, OFF_XB = 12 * U, OFF_T = 13 * U, OFF_D = OFF_T;
constexpr int OFF_BAR = 14 * U, OFF_SP = OFF_BAR + 512, OFF_G = OFF_SP + 1024 + 128;
constexpr int SMEM_BYTES = OFF_G + 512;
constexpr int B_FX = 0, B_FA = 8, B_FT = 12, B_Z = 16, B_W = 24, B_HX = 25, B_TL = 26, B_HP = 27, B_WR = 30, B_E0 = 34;
constexpr int B_EA = 35, B_ET = 39, B_PZ = 43, B_RDY = 45, B_FE = 46;
constexpr int B_T = 50, B_XS = 51, B_G = 53, NBAR = 54;
__host__ __device__ constexpr int rslot(int n) { return n & 3; }
__host__ __device__ constexpr int rpar(int n) { return (n >> 2) & 1; }

__global__ void __cluster_dims__(2, 1, 1) __launch_bounds__(512, 1)
fused_kernel(const __grid_constant__ Maps maps, const __nv_bfloat16* __restrict__ w_r,
             const __nv_bfloat16* __restrict__ w_i, const __nv_bfloat16* __restrict__ gate_w, __nv_bfloat16* __restrict__ out) {
  extern __shared__ __align__(1024) uint8_t smem[];
  const uint32_t sb = smem_u32(smem);
  const uint32_t bars = sb + OFF_BAR;
  const int tid = threadIdx.x, lane = tid & 31;
  const int warp = __shfl_sync(0xffffffffu, tid >> 5, 0);
  const bool helper = blockIdx.x >= 128;
  const int cl = (blockIdx.x >> 1) & 63, rank = blockIdx.x & 1;
  const int q4 = cl & 3, rb = cl >> 2;
  const int j = 2 * q4 + rank;
  const int f_full = 448 * q4 + (rank ? 256 : 0);
  const int f_half = 448 * q4 + (rank ? 224 : 192);
  const int kg = 2 * j + (rb >> 3), tn = rb & 7;

  if (tid == 64) { PROF_EV(0); PROF_CK(40); }
  if (warp < 8) {
    asm volatile("barrier.cluster.arrive.relaxed.aligned;" ::: "memory");
    asm volatile("setmaxnreg.inc.sync.aligned.u32 192;");
    if (!helper) {
      const int wg = warp >> 2, w = warp & 3, g = lane >> 2;
      const bool elect = (tid & 127) == 0;
      float cX[32], cA[64], cB[64], cC[64], ci[64], ct[64];
      const int zero = blockIdx.x >> 16;
      uint32_t h[56], yf[16];
      const uint32_t d0 = (sb & 0x3FFFF) >> 4;
      const uint32_t dK = d0 | (1u << 16), dN = d0 | (512u << 16);
      const uint32_t dX = dK + wg * 512;
      constexpr uint32_t RING = OFF_RING >> 4;
      auto waitA = [&](int n) { mbar_wait(bars + 8 * (B_FA + rslot(n)), rpar(n)); };
      auto freeA = [&](int n) { mbar_arrive_if(elect, bars + 8 * (B_EA + rslot(n))); };
      auto nop = [] {};

      asm volatile("bar.sync 0, 384;" ::: "memory");
#pragma unroll 1
      for (int i = 0; i < 4; i++) {
        const uint64_t dx = d128(dX + i * 2048), df = d128(dK + (OFF_XB >> 4) + (i & 1) * 1024);
        mbar_wait(bars + 8 * (B_FX + 2 * i), 0);
        wg_fence();
        mma_ss64<0, 0, 2>(cX, df, dx, i);
        mma_ss64<0, 0, 1>(cX, df + 2, dx + 2);
        wg_commit(); wg_wait<1>();
        mbar_arrive_if(elect && i, bars + 8 * (B_EA + rslot(i - 1)));
        mma_ss64<0, 0, 1>(cX, df + 4, dx + 4);
        mma_ss64<0, 0, 1>(cX, df + 6, dx + 6);
        if (i == 0 && tid == 0) PROF_EV(1);
        mbar_wait(bars + 8 * (B_FX + 2 * i + 1), 0);
        wg_fence();
#pragma unroll
        for (int k = 0; k < 4; k++) mma_ss64<0, 0, 1>(cX, df + (512 + k * 2), dx + (1024 + k * 2));
        wg_commit();
        waitA(i);
        wg_fence();
        const uint64_t da = d128(dX + i * 1024), db = d128(dN + RING + i * 1024);
        mma_ss128<0, 1, 2>(cA, da, db, i);
        wg_commit(); wg_wait<1>();
        mbar_arrive_if(elect, bars + 8 * (B_FE + i));
#pragma unroll
        for (int k = 1; k < 4; k++) mma_ss128<0, 1, 1>(cA, da + k * 2, db + k * 128);
        wg_commit();
      }
      fence_regs<0, 32>(cX);
#pragma unroll
      for (int e = 0; e < 16; e++) yf[e] = pack_pin(cX[2 * e], cX[2 * e + 1]);
      if (tid == 0) PROF_EV(2);
      {
        waitA(4); mbar_wait(bars + 8 * B_E0, 0);
        const uint64_t de = d128(dN + (wg ? RING : OFF_XB >> 4));
        wg_fence();
        mma_rs128<0, 1, 0>(cB, yf[0], yf[1], yf[2], yf[3], de);
        wg_commit();
        wg_wait<1>();
        freeA(3);
#pragma unroll
        for (int k = 1; k < 4; k++) mma_rs128<0, 1, 1>(cB, yf[4 * k], yf[4 * k + 1], yf[4 * k + 2], yf[4 * k + 3], de + k * 128);
        wg_commit();
      }
      bool rel = false;
      auto acquire = [&](int n) {
        rel = elect;
        if (!mbar_try(bars + 8 * (B_FA + rslot(n)), rpar(n))) { wg_wait<0>(); freeA(n - 1); rel = false; waitA(n); }
      };
      auto freeP = [&](int n) { mbar_arrive_if(rel, bars + 8 * (B_EA + rslot(n - 1))); };
      auto ffn_step = [&](auto first, auto split, float (&acc)[64], int n, int kb, auto done, auto work) {
        constexpr int SPLIT = decltype(split)::value;
        acquire(n);
        wg_fence();
        const uint64_t dx = d128(dX + kb * 1024), db = d128(dN + RING + rslot(n) * 1024);
        mma_ss128<0, 1, decltype(first)::value>(acc, dx, db, kb);
#pragma unroll
        for (int k = 1; k < SPLIT; k++) mma_ss128<0, 1, 1>(acc, dx + k * 2, db + k * 128);
        wg_commit();
        work();
        wg_wait<1>();
        freeP(n);
        done();
        if (SPLIT < 4) {
          wg_fence();
#pragma unroll
          for (int k = SPLIT; k < 4; k++) mma_ss128<0, 1, 1>(acc, dx + k * 2, db + k * 128);
          wg_commit();
        }
      };
      {
        const int s0 = 2 * rb + wg, kr = 2 * ((s0 & 1) | ((s0 & 4) >> 1));
        const int m = lane >> 3, r = lane & 7;
        const uint32_t a0 = sb + OFF_XB + wg * 8192 + (((w >> 1) * 8 + (m >> 1)) * 2 + (w & 1)) * 256 + (m & 1) * 128 + ((r ^ (kr + (m & 1))) << 4);
        ffn_step(IC<1>(), IC<4>(), cA, 5, 4, [&] { fence_regs<0, 64>(cB); }, nop);
        asm volatile("bar.sync 5, 256;" ::: "memory");
#pragma unroll
        for (int i = 0; i < 4; i++)
          stsm4t(a0 + i * 1024, pack_bf16(cB[8 * i] - cB[34 + 8 * i], cB[8 * i + 1] - cB[35 + 8 * i]),
                 pack_bf16(cB[32 + 8 * i] + cB[8 * i + 2], cB[33 + 8 * i] + cB[8 * i + 3]),
                 pack_bf16(cB[8 * i + 4] - cB[38 + 8 * i], cB[8 * i + 5] - cB[39 + 8 * i]),
                 pack_bf16(cB[36 + 8 * i] + cB[8 * i + 6], cB[37 + 8 * i] + cB[8 * i + 7]));
        if (j == 0 && w == 0) {
          const uint32_t a1 = r ? sb + OFF_SP + 1024 : sb + OFF_SP + wg * 512 + (m & 1) * 256 + (m >> 1) * 128;
#pragma unroll
          for (int n = 0; n < 8; n++)
            asm volatile("stmatrix.sync.aligned.m8n8.x4.shared.b16 [%0], {%1,%2,%3,%4};" ::"r"(a1 + ((n ^ (kr + (m >> 1))) << 4)),
                         "r"(pack_bf16(cB[4 * n], cB[4 * n + 1])), "r"(pack_bf16(cB[4 * n + 2], cB[4 * n + 3])),
                         "r"(pack_bf16(cB[32 + 4 * n], cB[33 + 4 * n])), "r"(pack_bf16(cB[34 + 4 * n], cB[35 + 4 * n])) : "memory");
        }
        ffn_step(IC<1>(), IC<2>(), cA, 6, 5, nop, [&] {
          asm volatile("fence.proxy.async.shared::cta;" ::: "memory");
          __syncwarp();
          mbar_arrive_if(lane == 0, bars + 8 * (B_XS + wg));
          if (tid == 0) PROF_EV(3);
        });
      }
#pragma unroll 1
      for (int kb = 6; kb < 8; kb++) ffn_step(IC<1>(), IC<1>(), cA, 1 + kb, kb, nop, nop);
      float g0 = 0.f, g1 = 0.f;
      uint32_t tag = 0;
      auto glu = [&](auto& acc, int half, int ho, int i0, int i1) {
#pragma unroll
        for (int i = i0; i < i1; i++) {
          const float o = 1.0f - ((i & 1) ? g1 : g0);
          asm volatile("" : "+f"(acc[2 * i]), "+f"(acc[2 * i + 1]), "+f"(acc[half + 2 * i]), "+f"(acc[half + 1 + 2 * i])::"memory");
          h[ho + i] = pack_pin(fmaxf(acc[2 * i], 0.f) * acc[half + 2 * i] * o, fmaxf(acc[2 * i + 1], 0.f) * acc[half + 1 + 2 * i] * o);
        }
      };
      ffn_step(IC<2>(), IC<1>(), cB, 9, zero, nop, nop);
#pragma unroll 1
      for (int kb = 1; kb < 8; kb++)
        ffn_step(IC<1>(), IC<1>(), cB, 9 + kb, kb, nop, [&] {
          if (kb == 4 + wg) {
            mbar_wait(bars + 8 * B_G, 0);
            const uint32_t gb0 = *(const uint32_t*)(smem + OFF_G + (wg * 64 + w * 16 + g) * 4), gb1 = *(const uint32_t*)(smem + OFF_G + (wg * 64 + w * 16 + g + 8) * 4);
            tag = gb0 & 1; g0 = __uint_as_float(gb0 & ~1u); g1 = __uint_as_float(gb1 & ~1u);
            glu(cA, 32, 0, 0, 8);
          } else if (kb == 6 + wg) glu(cA, 32, 0, 8, 16);
        });
      if (tid == 0) PROF_EV(4);
      ffn_step(IC<0>(), IC<1>(), cC, 17, 0, nop, nop);
#pragma unroll 1
      for (int kb = 1; kb < 8; kb++)
        ffn_step(IC<1>(), IC<1>(), cC, 17 + kb, kb, nop, [&] {
          if (kb == 1 + wg) glu(cB, 32, 16, 0, 8);
          else if (kb == 3 + wg) glu(cB, 32, 16, 8, 16);
        });
      if (tid == 0) PROF_EV(5);
      auto m_step = [&](auto first, int kb, auto work) {
        const int n = 25 + (kb >> 1);
        if (!(kb & 1)) acquire(n);
        wg_fence();
        const uint64_t dx = d128(dX + kb * 1024), dm = d64(dN + RING + rslot(n) * 1024 + (kb & 1) * 256);
        mma_ss64<0, 1, decltype(first)::value>(ct, dx, dm);
        mma_ss64<0, 1, 1>(ct, dx + 2, dm + 64);
        wg_commit();
        work();
        wg_wait<1>();
        mbar_arrive_if(rel && !(kb & 1), bars + 8 * (B_EA + rslot(n - 1)));
        mbar_arrive_if(elect && kb && !(kb & 1), bars + 8 * (B_ET + (kb >> 1) - 1));
        wg_fence();
        mma_ss64<0, 1, 1>(ct, dx + 4, dm + 128);
        mma_ss64<0, 1, 1>(ct, dx + 6, dm + 192);
        wg_commit();
      };
      auto freeT = [&](int t) { mbar_arrive_if(elect, bars + 8 * (B_ET + t)); };
      m_step(IC<0>(), 0, nop);
#pragma unroll 1
      for (int kb = 1; kb < 8; kb++)
        m_step(IC<1>(), kb, [&] {
          if (kb == 1 + 2 * wg) glu(cC, 32, 32, 0, 8);
          else if (kb == 5 + 2 * wg) glu(cC, 32, 32, 8, 16);
        });
      waitA(29 + wg);
      if (tid == 0) PROF_EV(6);
      if (tid == 128) PROF_EV(27);
      mbar_wait(bars + 8 * (j == 0 ? B_T : B_TL), 0);
      if (tid == 0) PROF_EV(7);
      wg_fence();
      {
        const uint64_t dt = d128(dN + (OFF_T >> 4) + wg * 512), de = d128(dK + RING + (1 + wg) * 1024);
        mma_ss64<0, 1, 0>(ci, de, dt);
        mma_ss64<32, 1, 0>(ci, de + 512, dt);
#pragma unroll
        for (int k = 1; k < 4; k++) {
          mma_ss64<0, 1, 1>(ci, de + k * 2, dt + k * 128);
          mma_ss64<32, 1, 1>(ci, de + (512 + k * 2), dt + k * 128);
        }
        wg_commit();
        wg_wait<1>();
        freeT(3);
        fence_regs<0, 32>(ct);
        glu(ct, 16, 48, 0, 8);
      }

      auto twait = [&](uint32_t bar, uint32_t par, int) { mbar_wait(bar, par); };
      auto fetch = [&](uint4 (&pv)[4], int z) {
        twait(bars + 8 * (z < 4 ? B_Z + 2 * z + wg : B_HP + z - 4), 0, 8 + z);
        const uint8_t* src = smem + (z < 4 ? OFF_Z + z * U : (z - 4) * U) + tid * 16;
#pragma unroll
        for (int i = 0; i < 4; i++) pv[i] = *(const uint4*)(src + i * 4096);
      };
      auto check = [&](uint4 (&pv)[4], int z) {
        const uint32_t t0 = (uint32_t)clock();
        while (__any_sync(0xffffffffu, ((pv[0].x ^ tag) | (pv[1].x ^ tag) | (pv[2].x ^ tag) | (pv[3].x ^ tag)) & 1)) {
#pragma unroll
          for (int i = 0; i < 4; i++) pv[i] = ld_x4(g_part + (size_t)((rb * 8 + j) * 3 + z - 4) * 1024 + tid + i * 256);
          spin_guard(t0);
        }
#pragma unroll
        for (int i = 0; i < 4; i++) pv[i].x &= ~1u;
      };
      auto head = [&](auto off, int t, bool init) {
        constexpr int O = decltype(off)::value;
        twait(bars + 8 * (B_FT + (t & 3)), t >> 2, t);
        const uint64_t db = d128(dN + (t & 3) * (TB >> 4) + rank * 256);
        wg_fence();
        mma_rs64<O, 1, 2>(ct, h[0], h[1], h[2], h[3], db, zero + init);
#pragma unroll
        for (int k = 1; k < 6; k++) mma_rs64<O, 1, 1>(ct, h[4 * k], h[4 * k + 1], h[4 * k + 2], h[4 * k + 3], db + k * 128);
        wg_commit();
        wg_wait<1>();
      };
      auto rest = [&](auto off, int t, int z) {
        constexpr int O = decltype(off)::value, P = 32 - O;
        const uint64_t db = d128(dN + (t & 3) * (TB >> 4)), dw = db + rank * 256, dm = db + (rank ? 0 : 1536);
        wg_fence();
#pragma unroll
        for (int k = 6; k < 12; k++) mma_rs64<O, 1, 1>(ct, h[4 * k], h[4 * k + 1], h[4 * k + 2], h[4 * k + 3], dw + k * 128);
        wg_commit();
        uint4 pv[4];
        if (z >= 0) fetch(pv, z);
        wg_fence();
#pragma unroll
        for (int k = 0; k < 2; k++) mma_rs64<O, 1, 1>(ct, h[48 + 4 * k], h[49 + 4 * k], h[50 + 4 * k], h[51 + 4 * k], dm + k * 128);
#pragma unroll
        for (int k = 0; k < 4; k++) mma_rs64<O, 1, 1>(ct, yf[4 * k], yf[4 * k + 1], yf[4 * k + 2], yf[4 * k + 3], db + (14 + k) * 128);
        wg_commit();
        if (z >= 0) {
          if (z >= 4) check(pv, z);
#pragma unroll
          for (int i = 0; i < 4; i++) {
            const uint32_t a[4] = {pv[i].x, pv[i].y, pv[i].z, pv[i].w};
#pragma unroll
            for (int e = 0; e < 4; e++) { ct[P + 8 * i + 2 * e] = bf_lo(a[e]); ct[P + 8 * i + 2 * e + 1] = bf_hi(a[e]); }
          }
        }
      };
      const uint32_t peerZ = mapa(sb + OFF_Z + tid * 16, rank ^ 1), peerB = mapa(bars + 8 * (B_Z + wg), rank ^ 1);
      auto send = [&](auto off, int t) {
        constexpr int O = decltype(off)::value;
        fence_regs<O, 32>(ct);
        const bool grid = t >= 3 && t < 6;
        const int z = grid ? t - 3 : t == 6 ? 3 : t;
        uint32_t pk[16];
#pragma unroll
        for (int i = 0; i < 16; i++) pk[i] = pack_bf16(ct[O + 2 * i], ct[O + 2 * i + 1]);
        if (grid) {
          const int owner = rb * 8 + 2 * ((q4 + z + 1) & 3) + rank;
          uint4* dst = g_part + (size_t)(owner * 3 + z) * 1024 + tid;
#pragma unroll
          for (int i = 0; i < 4; i++) st_x4(dst + i * 256, (pk[4 * i] & ~1u) | tag, pk[4 * i + 1], pk[4 * i + 2], pk[4 * i + 3]);
          __syncwarp();
          hint_add_if(lane == 0, &g_cntP[32 * owner + z]);
        } else {
#pragma unroll
          for (int i = 0; i < 4; i++)
            asm volatile("st.async.weak.shared::cluster.mbarrier::complete_tx::bytes.v4.b32 [%0], {%1,%2,%3,%4}, [%5];" ::"r"(peerZ + z * U + i * 4096),
                         "r"(pk[4 * i]), "r"(pk[4 * i + 1]), "r"(pk[4 * i + 2]), "r"(pk[4 * i + 3]), "r"(peerB + 16 * z) : "memory");
        }
      };
      asm volatile("barrier.cluster.wait.aligned;" ::: "memory");
      head(IC<0>(), 0, false);
      if (elect) asm volatile("mbarrier.arrive.shared::cluster.b64 _, [%0];" ::"r"(mapa(bars + 8 * B_RDY, rank ^ 1)) : "memory");
      fence_regs<0, 64>(ci);
#pragma unroll
      for (int i = 0; i < 16; i++) {
        const float gg = ((i & 1) ? g1 : g0) * (2.0f / (2048.0f * 512.0f));
        if (i & 2) yf[i] = pack_pin((ci[2 * i] - ci[28 + 2 * i]) * gg, (ci[2 * i + 1] - ci[29 + 2 * i]) * gg);
        else yf[i] = pack_pin((ci[2 * i] + ci[36 + 2 * i]) * gg, (ci[2 * i + 1] + ci[37 + 2 * i]) * gg);
      }
      if (tid == 0) PROF_EV(8);
      if (tid == 128) PROF_EV(28);
#pragma unroll 1
      for (int t = 0;; t += 2) {
        rest(IC<0>(), t, t - 2);
        head(IC<32>(), t + 1, t >= 2);
        mbar_arrive_if(elect && t < 6, bars + 8 * (B_ET + t));
        if (t == 0) twait(bars + 8 * B_RDY, 0, 15);
        send(IC<0>(), t);
        rest(IC<32>(), t + 1, (t & 2) ? t - 1 : -1);
        if (t == 6) break;
        head(IC<0>(), t + 2, t == 2);
        mbar_arrive_if(elect, bars + 8 * (B_ET + t + 1));
        send(IC<32>(), t + 1);
      }
      if (tid == 0) PROF_EV(9);
      if (tid == 128) PROF_EV(29);
      {
        float (&sum)[64] = ct;
        uint4 p2[4], p3[4];
        fetch(p3, 3);
        if (tid == 0) PROF_EV(25);
        fetch(p2, 6);
        if (tid == 0) PROF_EV(24);
        check(p2, 6);
#pragma unroll
        for (int i = 0; i < 4; i++) {
          const uint32_t b[4] = {p2[i].x, p2[i].y, p2[i].z, p2[i].w}, c[4] = {p3[i].x, p3[i].y, p3[i].z, p3[i].w};
#pragma unroll
          for (int e = 0; e < 4; e++) {
            sum[8 * i + 2 * e] += bf_lo(c[e]) + bf_lo(b[e]);
            sum[8 * i + 2 * e + 1] += bf_hi(c[e]) + bf_hi(b[e]);
          }
        }
        if (tid == 0) PROF_EV(14);
        wg_wait<0>();
        fence_regs<32, 32>(ct);
#pragma unroll
        for (int i = 0; i < 32; i++) sum[i] += ct[32 + i];
        const uint32_t stg = sb + OFF_T + warp * 2048;
        const int mr = (lane & 7) + ((lane >> 3) & 1) * 8, mc = lane >> 4;
#pragma unroll
        for (int i = 0; i < 4; i++) {
          const uint32_t a = stg + mr * 128 + (((2 * i + mc) ^ (mr & 7)) << 4);
          asm volatile("stmatrix.sync.aligned.m8n8.x4.shared.b16 [%0], {%1,%2,%3,%4};" ::"r"(a), "r"(pack_bf16(sum[8 * i], sum[8 * i + 1])),
                       "r"(pack_bf16(sum[8 * i + 2], sum[8 * i + 3])), "r"(pack_bf16(sum[8 * i + 4], sum[8 * i + 5])),
                       "r"(pack_bf16(sum[8 * i + 6], sum[8 * i + 7])) : "memory");
        }
        __syncwarp();
#pragma unroll
        for (int i = 0; i < 4; i++) {
          const int r = 4 * i + (lane >> 3), c = lane & 7;
          const uint4 v = *(const uint4*)(smem + OFF_T + warp * 2048 + r * 128 + ((c ^ (r & 7)) << 4));
          *(uint4*)(out + (size_t)(2 * rb + wg + 32 * (16 * w + r)) * 512 + 64 * j + 8 * c) = v;
        }
      }
      if (tid == 0) { PROF_EV(15); PROF_CK(41); }
      if (tid == 128) PROF_EV(30);
    }
  } else if (warp < 12) {
    asm volatile("setmaxnreg.dec.sync.aligned.u32 104;");
    asm volatile("barrier.cluster.arrive.relaxed.aligned;" ::: "memory");
    const int t = tid - 256, w = warp - 8;
    const uint32_t ep = ld_x1(&g_epoch[blockIdx.x * 8]);
    const uint32_t tag = (ep + 1) & 1;
    auto w_issue = [&](const CUtensorMap* m) {
          if (elect_one()) { mbar_expect_tx(bars + 8 * (B_WR + w), 3072); tma4d(sb + OFF_T + w * 3072, m, bars + 8 * (B_WR + w), 16 * kg, 0, 2 * w, tn); }
          __syncwarp();
    };
    auto gate_rows = [&] {
      const int r = 16 * j + 4 * w + (lane >> 3);
      const uint4* pg = (const uint4*)gate_w + (lane & 7);
      {
        float a = 0.f;
        asm volatile("bar.sync 4, 256;" ::: "memory");
#pragma unroll 1
        for (int hf = 0; hf < 2; hf++) {
          uint4 v[4], u[4];
#pragma unroll
          for (int kb = 0; kb < 4; kb++) v[kb] = __ldg(pg + (4 * hf + kb) * 8);
          mbar_wait(bars + 8 * (B_FE + 1 + 2 * hf), 0);
          if (hf) w_issue(&maps.wr);
#pragma unroll
          for (int kb = 0; kb < 4; kb++) u[kb] = *(const uint4*)(smem + (4 * hf + kb) * U + r * 128 + (((lane ^ r) & 7) << 4));
#pragma unroll
          for (int kb = 0; kb < 4; kb++) {
            a = fmaf(bf_lo(u[kb].x), bf_lo(v[kb].x), a); a = fmaf(bf_hi(u[kb].x), bf_hi(v[kb].x), a);
            a = fmaf(bf_lo(u[kb].y), bf_lo(v[kb].y), a); a = fmaf(bf_hi(u[kb].y), bf_hi(v[kb].y), a);
            a = fmaf(bf_lo(u[kb].z), bf_lo(v[kb].z), a); a = fmaf(bf_hi(u[kb].z), bf_hi(v[kb].z), a);
            a = fmaf(bf_lo(u[kb].w), bf_lo(v[kb].w), a); a = fmaf(bf_hi(u[kb].w), bf_hi(v[kb].w), a);
          }
        }
#pragma unroll
        for (int o = 4; o; o >>= 1) a += __shfl_xor_sync(0xffffffffu, a, o);
        if ((lane & 7) == 0)
          asm volatile("st.relaxed.gpu.global.f32 [%0], %1;" ::"l"(g_gate + rb * 128 + r), "f"(tagf(__fdividef(1.0f, 1.0f + __expf(-a)), tag)) : "memory");
        if (t == 0) PROF_EV(18);
      }
    };
    {
      const int g = lane >> 2, q = lane & 3;
      uint32_t wf[32];
      if (!helper) {
        gate_rows();
        const uint32_t wa = sb + OFF_T + w * (3072 + 4) + q * 48 + g * 2;
#pragma unroll 1
        for (int ri = 0; ri < 2; ri++) {
          mbar_wait(bars + 8 * (B_WR + w), ri);
#pragma unroll
          for (int n2 = 0; n2 < NOLDS; n2++) {
            uint32_t v[16];
#pragma unroll
            for (int i = 0; i < 16; i++)
              asm volatile("ld.shared.u16 %0, [%1];" : "=r"(v[i]) : "r"(wa + (4 * n2 + ((i >> 1) & 3)) * 192 + (i & 1) * (1536 + 2) + (i >> 3) * 16) : "memory");
#pragma unroll
            for (int i = 0; i < 16; i++) {
              uint32_t& d = wf[(i >> 3) * 16 + 8 * n2 + (i & 7)];
              d = __byte_perm(d, v[i], 0x5432);
              asm volatile("" : "+r"(d)::"memory");
            }
          }
          __syncwarp();
          if (ri == 0) w_issue(&maps.wi);
        }
        asm volatile("bar.sync 1, 128;" ::: "memory");
        if (t == 0) PROF_EV(11);
      } else {
        asm volatile("bar.sync 4, 256;" ::: "memory");
        hint_wait(&g_cntW[0], (ep + 1) * 128u);
        const uint32_t t0 = (uint32_t)clock();
#pragma unroll 1
        for (;;) {
          uint32_t bad = 0;
#pragma unroll
          for (int i = 0; i < 32; i++) {
            const float2 v = ld_x2((const float2*)g_Wh + (i >> 4) * 2048 + 16 * w + g + 8 * (i & 1) + 64 * q + ((i >> 1) & 7) * 256);
            wf[i] = __float_as_uint(v.x); bad |= __float_as_uint(v.y) ^ tag;
          }
          if (!__any_sync(0xffffffffu, bad & 1)) break;
          spin_guard(t0);
        }
        if (t == 0) PROF_EV(11);
      }
      if (w == 0 && elect_one()) { mbar_expect_tx(bars + 8 * B_W, 8192); bulk_load(sb + OFF_D, g_DT.v, 8192, bars + 8 * B_W); }
      if (!helper) {
        const uint32_t t0 = (uint32_t)clock();
        uint32_t v;
        do { v = ld_x1(g_gate + rb * 128 + t); spin_guard(t0); } while (__any_sync(0xffffffffu, (v ^ tag) & 1));
        *(uint32_t*)(smem + OFF_G + t * 4) = v;
        __syncwarp();
        mbar_arrive_if(lane == 0, bars + 8 * B_G);
      }
      mbar_wait(bars + 8 * B_W, 0);
      mbar_wait(bars + 8 * B_HX, 0);
      if (t == 0) PROF_EV(12);
      const uint32_t dd = (sb & 0x3FFFF) >> 4;
      const uint64_t dF = d128((dd + (OFF_D >> 4)) | (512u << 16)), dI = d128((dd + (OFF_D >> 4)) | (1u << 16)), dA = d128((dd + (OFF_XB >> 4)) | (512u << 16));
      float az[32];
      const int zero = blockIdx.x >> 16;
      uint32_t pf[32];
#pragma unroll
      for (int mt = 0; mt < 2; mt++) {
        wg_fence();
        if (mt == 0) mma_ss64<0, 3, 0>(az, dA, dF);
        else mma_ss64<0, 3, 2>(az, dA + 512, dF, zero);
#pragma unroll
        for (int k = 1; k < 4; k++) mma_ss64<0, 3, 1>(az, dA + (mt * 512 + k * 128), dF + k * 128);
        wg_commit();
        wg_wait<0>();
        fence_regs<0, 32>(az);
#pragma unroll
        for (int i = 0; i < 16; i++) {
          const float wr = bf_lo(wf[16 * mt + i]), wi = bf_hi(wf[16 * mt + i]);
          pf[16 * mt + i] = pack_pin(fmaf(az[2 * i], wr, -az[2 * i + 1] * wi), fmaf(az[2 * i], wi, az[2 * i + 1] * wr));
        }
      }
      if (t == 0) PROF_EV(16);
#pragma unroll
      for (int mt = 0; mt < 2; mt++) {
        wg_fence();
        mma_rs64<0, 0, 2>(az, pf[16 * mt], pf[16 * mt + 1], pf[16 * mt + 2], pf[16 * mt + 3], dI, mt ? (int)helper : zero);
#pragma unroll
        for (int k = 1; k < 4; k++) mma_rs64<0, 0, 1>(az, pf[16 * mt + 4 * k], pf[16 * mt + 4 * k + 1], pf[16 * mt + 4 * k + 2], pf[16 * mt + 4 * k + 3], dI + k * 2);
        wg_commit();
        wg_wait<0>();
        fence_regs<0, 32>(az);
        if (!helper) {
          const int m = lane >> 3, r = lane & 7;
          const int sl = 2 * (m >> 1) + ((r >> 1) & 1) + 4 * (r >> 2);
          const uint32_t a0 = sb + OFF_XB + (2 * w + (m & 1)) * 2048 + sl * 64 + (((mt * 2 + (r & 1)) ^ (sl >> 1)) << 4);
#pragma unroll
          for (int i = 0; i < 4; i++)
            stsm4t(a0 + i * 512, pack_bf16(az[8 * i], az[8 * i + 1]), pack_bf16(az[8 * i + 2], az[8 * i + 3]), pack_bf16(az[8 * i + 4], az[8 * i + 5]),
                   pack_bf16(az[8 * i + 6], az[8 * i + 7]));
        }
      }
      if (helper) {
#pragma unroll
        for (int i = 0; i < 16; i++) {
          const int n = i >> 1, s0 = 8 * (n >> 1) + 2 * (n & 1) + (q & 1) + 4 * (q >> 1);
          if ((n & 1) == (int)(blockIdx.x & 1)) st_u2(g_Ts + s0 * 64 + 16 * w + g + 8 * (i & 1), pack_bf16(az[2 * i], az[2 * i + 1]), tag);
        }
        __syncwarp();
        hint_add_if(lane == 0, &g_cntH[0]);
        if (t == 0) { g_epoch[blockIdx.x * 8] = ep + 1; PROF_EV(13); }
      } else {
        asm volatile("fence.proxy.async.shared::cta;" ::: "memory");
        __syncwarp();
        if (elect_one()) {
          if (t == 0) PROF_EV(17);
          if (SPACE) __nanosleep(SPACE * w);
          asm volatile("cp.async.bulk.tensor.3d.global.shared::cta.bulk_group [%0, {%2, %3, %4}], [%1];" ::"l"(&maps.ts), "r"(sb + OFF_XB + w * 4096),
                       "r"(32 * kg), "r"(0), "r"(8 * tn + 2 * w) : "memory");
          bulk_done_signal(&g_cntT[32 * j]);
          if (t == 96) PROF_EV(13);
        }
        __syncwarp();
        if (j == 0) {
          hint_wait(&g_cntH[0], (ep + 1) * 8u);
          const uint32_t t0 = (uint32_t)clock();
          float2 v;
          do { v = ld_x2((const float2*)g_Ts + 2 * rb * 64 + t); spin_guard(t0); } while (__any_sync(0xffffffffu, (__float_as_uint(v.y) ^ tag) & 1));
          mbar_wait(bars + 8 * B_TL, 0);
          const uint32_t u = __float_as_uint(v.x);
          *(uint16_t*)(smem + OFF_T + t * 128 + ((t & 7) << 4)) = (uint16_t)u;
          *(uint16_t*)(smem + OFF_T + t * 128 + (((t & 7) ^ 1) << 4)) = (uint16_t)(u >> 16);
          asm volatile("fence.proxy.async.shared::cta;" ::: "memory");
          __syncwarp();
          mbar_arrive_if(lane == 0, bars + 8 * B_T);
        }
      }
    }
  } else {
    asm volatile("setmaxnreg.dec.sync.aligned.u32 24;");
    auto xf_load = [&](int q) {
      const uint32_t fb = bars + 8 * (B_FX + q);
      mbar_expect_tx(fb, U + 8192);
      tma3d(sb + q * U, &maps.x, fb, 64 * q, 0, 2 * rb);
      if (q >= 4) mbar_wait(bars + 8 * (B_FE + ((q - 4) >> 1)), 0);
      tma2d(sb + OFF_XB + (q & 3) * 8192, &maps.ft, fb, 64 * q, 64 * j);
    };
    if (elect_one()) {
      if (warp == 14) {
#pragma unroll
        for (int i = 0; i < B_FT; i++) mbar_init(bars + 8 * i, 1);
        asm volatile("fence.proxy.async.shared::cta;" ::: "memory");
        if (!helper) {
#pragma unroll 1
          for (int n = 0; n < 2; n++) {
            const uint32_t fb = bars + 8 * (B_FA + n);
            xf_load(2 * n); xf_load(2 * n + 1);
            mbar_expect_tx(fb, U);
            tma2d(sb + OFF_RING + n * U, &maps.g64, fb, f_full, 64 * n);
            tma2d(sb + OFF_RING + n * U + 8192, &maps.u64, fb, f_full, 64 * n);
          }
        }
      } else if (warp == 15) {
#pragma unroll
        for (int i = B_FT; i < NBAR; i++) mbar_init(bars + 8 * i, i < B_EA ? 1 : i < B_T ? 2 : 4);
#pragma unroll
        for (int i = 0; i < 8; i++) mbar_expect_tx(bars + 8 * (B_Z + i), U / 2);
        asm volatile("fence.mbarrier_init.release.cluster;" ::: "memory");
        asm volatile("fence.proxy.async.shared::cta;" ::: "memory");
      } else if (warp == 13) {
#pragma unroll
        for (int i = 1; i < 4; i++) asm volatile("prefetch.tensormap [%0];" ::"l"((const char*)&maps + i * 128) : "memory");
      }
    }
    __syncwarp();
    asm volatile("bar.arrive 0, 384;" ::: "memory");
    asm volatile("bar.arrive 4, 256;" ::: "memory");
    __syncwarp();
    asm volatile("barrier.cluster.arrive.relaxed.aligned;" ::: "memory");
    asm volatile("bar.sync 3, 128;" ::: "memory");
    if (warp == 15 && !helper) {
        mbar_wait(bars + 8 * B_FE, 0);
        const uint32_t tag = (ld_x1(&g_epoch[blockIdx.x * 8]) + 1) & 1;
        const int c = lane >> 4, jj = 16 * blockIdx.x + (lane & 15), jm = (2048 - jj) & 2047;
        const unsigned short* pr = (const unsigned short*)w_r + 256 * c;
        const unsigned short* pi = (const unsigned short*)w_i + 256 * c;
        const float wr = 0.25f * (bf_lo(__ldg(pr + jj * 257)) + bf_lo(__ldg(pr + jm * 257)));
        const float wi = 0.25f * (bf_lo(__ldg(pi + jj * 257)) - bf_lo(__ldg(pi + jm * 257)));
        st_u2(g_Wh + c * 2048 + jj, c ? pack_bf16(-wi, wr) : pack_bf16(wr, wi), tag);
        __syncwarp();
        hint_add_if(lane == 0, &g_cntW[0]);
      }
    if ((!helper || warp == 15) && elect_one()) {
      if (warp < 14) {
        const int p = warp - 12;
#pragma unroll 1
        for (int n = 2; n < 31; n++) {
          const bool table = n == 4 || n >= 29;
          const int q = n < 4 ? n : n - 1;
          const CUtensorMap* m = table ? &maps.e : n >= 25 ? &maps.g32 + p : &maps.g64 + p;
          const int c0 = table ? 0 : n >= 25 ? f_half : f_full + 64 * (q >> 3);
          const int c1 = table ? (2 * rb + ((n & 1) ^ 1)) * 128 + 64 * p : n >= 25 ? 128 * (n - 25) : 64 * (q & 7);
          const uint32_t fb = bars + 8 * (B_FA + (n & 3)), dst = sb + OFF_RING + (n & 3) * U + p * 8192;
          if (n < 4) mbar_wait(bars + 8 * (B_FE + n - 2), 0);
          else mbar_wait(bars + 8 * (B_EA + (n & 3)), ((n >> 2) & 1) ^ 1);
          tma2d(dst, m, fb, c0, c1);
          if (p == 0) mbar_expect_tx(fb, U);
        }
      } else if (warp == 15) {
        const unsigned ep1 = ld_x1(&g_epoch[blockIdx.x * 8]) + 1;
        flag_wait(&g_cntX[helper ? 0 : 32 * j], ep1 * 16u);
        PROF_EV(22);
        mbar_expect_tx(bars + 8 * B_HX, U);
        bulk_load(sb + OFF_XB, g_X + (size_t)(helper ? 128 : kg * 8 + tn) * 8192, U, bars + 8 * B_HX);
        if (!helper) {
          flag_wait(&g_cntT[32 * j], ep1 * 64u);
          PROF_EV(23);
          mbar_expect_tx(bars + 8 * B_TL, U);
          tma3d(sb + OFF_T, &maps.t, bars + 8 * B_TL, 64 * j, 0, 2 * rb);
#pragma unroll 1
          for (int i = 0; i < 3; i++) {
            mbar_wait(bars + 8 * (B_PZ + (i >> 1)), 0);
            flag_wait(&g_cntP[32 * (rb * 8 + j) + i], ep1 * 8u);
            if (i == 2) PROF_EV(26);
            mbar_expect_tx(bars + 8 * (B_HP + i), U);
            bulk_load(sb + i * U, g_part + (size_t)((rb * 8 + j) * 3 + i) * 1024, U, bars + 8 * (B_HP + i));
          }
          g_epoch[blockIdx.x * 8] = ep1;
        }
      } else {
#pragma unroll 1
        for (int q = 4; q < 8; q++) xf_load(q);
        mbar_wait(bars + 8 * (B_FE + 2), 0);
        mbar_expect_tx(bars + 8 * B_E0, U);
        tma2d(sb + OFF_XB, &maps.e, bars + 8 * B_E0, 0, 2 * rb * 128);
        tma2d(sb + OFF_XB + 8192, &maps.e, bars + 8 * B_E0, 0, 2 * rb * 128 + 64);
#pragma unroll 1
        for (int h2 = 0; h2 < 2; h2++) {
          const int s0 = 2 * rb + h2, sg = (s0 & ~6) | ((s0 & 2) << 1) | ((s0 & 4) >> 1);
          mbar_wait(bars + 8 * (B_XS + h2), 0);
#pragma unroll 1
          for (int c = 0; c < 2; c++) {
            asm volatile("cp.async.bulk.tensor.4d.global.shared::cta.bulk_group [%0, {%2, %3, %4, %5}], [%1];" ::"l"(&maps.xs),
                         "r"(sb + OFF_XB + h2 * 8192 + c * 4096), "r"(0), "r"(sg), "r"(0), "r"(16 * j + 8 * c) : "memory");
            if (j == 0)
              asm volatile("cp.async.bulk.global.shared::cta.bulk_group [%0], [%1], 256;" ::"l"(g_X + 128 * 8192 + c * 4096 + sg * 128),
                           "r"(sb + OFF_SP + h2 * 512 + c * 256) : "memory");
            if (SPACE && h2 + c < 2) __nanosleep(SPACE);
          }
        }
        bulk_done_signal(&g_cntX[32 * j]);
        PROF_EV(20);
#pragma unroll 1
        for (int t = 0; t < 8; t++) {
          const int i = t < 3 ? t + 1 : t < 6 ? t - 2 : 0;
          const int col = 64 * (2 * ((q4 + i) & 3) + ((t < 3 || t == 6) ? 1 - rank : rank));
          const uint32_t fb = bars + 8 * (B_FT + (t & 3)), dst = sb + (t & 3) * TB;
          mbar_wait(bars + 8 * (B_ET + (t == 2 ? 3 : t & 3)), t >> 2);
          mbar_expect_tx(fb, TB);
          tma2d(dst, &maps.d224, fb, col, 224 * j);
          if (t < 2) mbar_wait(bars + 8 * (B_ET + t + 1), 0);
          tma2d(dst + 28672, &maps.ft, fb, col, 64 * j);
        }
      }
    }
  }
}

typedef CUresult (*EncodeFn)(CUtensorMap*, CUtensorMapDataType, cuuint32_t, void*, const cuuint64_t*, const cuuint64_t*, const cuuint32_t*,
                             const cuuint32_t*, CUtensorMapInterleave, CUtensorMapSwizzle, CUtensorMapL2promotion, CUtensorMapFloatOOBfill);

static void encode(EncodeFn f, CUtensorMap* m, const void* base, int rank, const cuuint64_t* dims, const cuuint64_t* strides, const cuuint32_t* box,
                   CUtensorMapSwizzle sw) {
  cuuint32_t es[5] = {1, 1, 1, 1, 1};
  f(m, CU_TENSOR_MAP_DATA_TYPE_BFLOAT16, rank, (void*)base, dims, strides, box, es, CU_TENSOR_MAP_INTERLEAVE_NONE, sw,
    CU_TENSOR_MAP_L2_PROMOTION_L2_128B, CU_TENSOR_MAP_FLOAT_OOB_FILL_NONE);
}

extern "C" void kernel_launch(void* const* d_in, const int* in_sizes, int n_in, void* d_out, int out_size) {
  (void)in_sizes; (void)n_in; (void)out_size;
  const __nv_bfloat16* x = (const __nv_bfloat16*)d_in[0];
  const __nv_bfloat16* w_r = (const __nv_bfloat16*)d_in[1];
  const __nv_bfloat16* w_i = (const __nv_bfloat16*)d_in[2];
  const __nv_bfloat16* Wg = (const __nv_bfloat16*)d_in[4];
  const __nv_bfloat16* Wu = (const __nv_bfloat16*)d_in[5];
  const __nv_bfloat16* Wd = (const __nv_bfloat16*)d_in[6];
  const __nv_bfloat16* gw = (const __nv_bfloat16*)d_in[7];

  void* fp = nullptr; cudaDriverEntryPointQueryResult qr;
  cudaGetDriverEntryPoint("cuTensorMapEncodeTiled", &fp, cudaEnableDefault, &qr);
  EncodeFn enc = (EncodeFn)fp;
  void *pFT, *pET, *pX, *pT;
  cudaGetSymbolAddress(&pX, g_X); cudaGetSymbolAddress(&pT, g_T);
  cudaGetSymbolAddress(&pFT, g_FT); cudaGetSymbolAddress(&pET, g_ET);

  Maps mp;
  const CUtensorMapSwizzle S128 = CU_TENSOR_MAP_SWIZZLE_128B, S64 = CU_TENSOR_MAP_SWIZZLE_64B;
  { cuuint64_t d[3] = {512, 64, 32}, s[2] = {32768, 1024}; cuuint32_t b[3] = {64, 64, 2}; encode(enc, &mp.x, x, 3, d, s, b, S128); }
  { cuuint64_t d[2] = {512, 512}, s[1] = {1024}; cuuint32_t b[2] = {64, 64}; encode(enc, &mp.ft, pFT, 2, d, s, b, S128); }
  { cuuint64_t d[4] = {128, 32, 2, 129}, s[3] = {256, 8192, 16384}; cuuint32_t b[4] = {128, 1, 2, 8}; encode(enc, &mp.xs, pX, 4, d, s, b, CU_TENSOR_MAP_SWIZZLE_NONE); }
  { cuuint64_t d[3] = {512, 32, 64}, s[2] = {65536, 1024}; cuuint32_t b[3] = {32, 32, 2}; encode(enc, &mp.ts, pT, 3, d, s, b, S64); }
  { cuuint64_t d[3] = {512, 64, 32}, s[2] = {1024, 65536}; cuuint32_t b[3] = {64, 64, 2}; encode(enc, &mp.t, pT, 3, d, s, b, S128); }
  { cuuint64_t d[2] = {64, 4096}, s[1] = {128}; cuuint32_t b[2] = {64, 64}; encode(enc, &mp.e, pET, 2, d, s, b, S128); }
  { cuuint64_t d[2] = {1792, 512}, s[1] = {3584}; cuuint32_t b[2] = {64, 64}, b2[2] = {32, 128};
    encode(enc, &mp.g64, Wg, 2, d, s, b, S128); encode(enc, &mp.u64, Wu, 2, d, s, b, S128);
    encode(enc, &mp.g32, Wg, 2, d, s, b2, S64); encode(enc, &mp.u32, Wu, 2, d, s, b2, S64); }
  { cuuint64_t d[2] = {512, 1792}, s[1] = {1024}; cuuint32_t b[2] = {64, 224}; encode(enc, &mp.d224, Wd, 2, d, s, b, S128); }
  { cuuint64_t d[4] = {264, 32, 8, 8}, s[3] = {32896, 512, 4112}; cuuint32_t b[4] = {24, 32, 2, 1};
    encode(enc, &mp.wr, w_r, 4, d, s, b, CU_TENSOR_MAP_SWIZZLE_NONE); encode(enc, &mp.wi, w_i, 4, d, s, b, CU_TENSOR_MAP_SWIZZLE_NONE); }

  cudaFuncSetAttribute(fused_kernel, cudaFuncAttributeMaxDynamicSharedMemorySize, SMEM_BYTES);
  fused_kernel<<<NCTA, 512, SMEM_BYTES>>>(mp, w_r, w_i, gw, (__nv_bfloat16*)d_out);
}
```

```cpp
#include <cuda_runtime.h>
#include <cuda_bf16.h>
#include <cuda.h>
#include <stdint.h>

namespace tbl {
constexpr double PI = 3.14159265358979323846264338327950288;
constexpr double sin_s(double x) { double t = x, s = x; for (int n = 1; n < 12; n++) { t *= -x * x / ((2 * n) * (2 * n + 1)); s += t; } return s; }
constexpr double cos_s(double x) { double t = 1, s = 1; for (int n = 1; n < 12; n++) { t *= -x * x / ((2 * n - 1) * (2 * n)); s += t; } return s; }
constexpr double cos2048(int m) {
  m &= 2047; if (m > 1024) m = 2048 - m;
  bool neg = false; if (m > 512) { m = 1024 - m; neg = true; }
  double v = (m <= 256) ? cos_s(2 * PI * m / 2048) : sin_s(2 * PI * (512 - m) / 2048);
  return neg ? -v : v;
}
constexpr uint16_t to_bf16(double v) {
  if (v == 0) return 0;
  uint16_t s = 0; if (v < 0) { s = 0x8000; v = -v; }
  int e = 0; while (v >= 2) { v /= 2; e++; } while (v < 1) { v *= 2; e--; }
  double m = (v - 1) * 128; int mi = (int)m; double fr = m - mi;
  if (fr > 0.5 || (fr == 0.5 && (mi & 1))) mi++;
  if (mi == 128) { mi = 0; e++; }
  return (uint16_t)(s | ((e + 127) << 7) | mi);
}
struct CosT { uint16_t v[2048]; constexpr CosT() : v() { for (int i = 0; i < 2048; i++) v[i] = to_bf16(cos2048(i)); } };
struct alignas(1024) FT {
  uint16_t v[512 * 512];
  constexpr FT() : v() {
    CosT c;
    for (int r = 0; r < 512; r++) {
      int k = (r >> 4) * 8 + (r & 7), e = (r >> 3) & 1;
      int mul = 4 * k, add = e ? 512 : 0;
      if (k == 0 && e == 1) { mul = 1024; add = 0; }
      for (int d = 0; d < 512; d++) v[r * 512 + d] = c.v[(d * mul + add) & 2047];
    }
  }
};
struct alignas(1024) ET {
  uint16_t v[2048 * 128];
  constexpr ET() : v() {
    CosT c;
    for (int s = 0; s < 2048; s++)
      for (int j = 0; j < 64; j++) {
        const int o = (s & 31) * 8192 + (s >> 5) * 64 + j;
        v[o] = c.v[(s * j) & 2047]; v[o + 4096] = c.v[(s * j + 512) & 2047];
      }
  }
};
struct alignas(1024) DT {
  uint16_t v[64 * 64];
  constexpr DT() : v() {
    CosT c;
    for (int r = 0; r < 64; r++)
      for (int n = 0; n < 64; n++) {
        const int sg = r >> 1, s0 = (sg & ~6) | ((sg & 2) << 1) | ((sg & 4) >> 1), e = r & 1, f = n & 1;
        const int m = 64 * s0 * (n >> 1) + (e == f ? 0 : e ? -512 : 512);
        v[r * 64 + (((n >> 3) ^ (r & 7)) << 3) + (n & 7)] = c.v[m & 2047];
      }
  }
};
}

__device__ constexpr tbl::FT g_FT = tbl::FT();
__device__ constexpr tbl::ET g_ET = tbl::ET();
__device__ constexpr tbl::DT g_DT = tbl::DT();

__device__ __align__(1024) uint16_t g_X[129 * 8192];
__device__ __align__(1024) uint16_t g_T[32 * 64 * 512];
__device__ __align__(1024) uint2 g_Ts[32 * 64];
__device__ __align__(1024) uint4 g_part[128 * 3 * 1024];
__device__ __align__(16) float g_gate[16 * 128];
__device__ __align__(16) uint2 g_Wh[2 * 2048];
__device__ unsigned g_epoch[132 * 8];
__device__ unsigned g_cntX[8 * 32], g_cntT[8 * 32], g_cntP[128 * 32], g_cntW[32], g_cntH[32];
#define PROF_EV(i) do {} while (0)
#define PROF_CK(i) do {} while (0)

__device__ __forceinline__ uint32_t smem_u32(const void* p) { return (uint32_t)__cvta_generic_to_shared(p); }
__device__ __forceinline__ void mbar_init(uint32_t bar, uint32_t cnt) { asm volatile("mbarrier.init.shared::cta.b64 [%0], %1;" ::"r"(bar), "r"(cnt)); }
__device__ __forceinline__ void mbar_expect_tx(uint32_t bar, uint32_t bytes) { asm volatile("mbarrier.arrive.expect_tx.shared::cta.b64 _, [%0], %1;" ::"r"(bar), "r"(bytes) : "memory"); }
__device__ __forceinline__ void mbar_arrive(uint32_t bar) { asm volatile("mbarrier.arrive.shared::cta.b64 _, [%0];" ::"r"(bar) : "memory"); }
__device__ __forceinline__ bool elect_one() {
  uint32_t p;
  asm volatile("{\n.reg .pred p;\nelect.sync _|p, 0xffffffff;\nselp.u32 %0, 1, 0, p;\n}" : "=r"(p));
  return p;
}
__device__ __forceinline__ void mbar_arrive_if(bool p, uint32_t bar) {
  asm volatile("{\n.reg .pred p;\nsetp.ne.b32 p, %1, 0;\n@p mbarrier.arrive.shared::cta.b64 _, [%0];\n}" ::"r"(bar), "r"((int)p) : "memory");
}
__device__ __forceinline__ void hint_add_if(bool p, unsigned* a) {
  asm volatile("{\n.reg .pred p;\nsetp.ne.b32 p, %1, 0;\n@p red.relaxed.gpu.global.add.u32 [%0], 1;\n}" ::"l"(a), "r"((int)p) : "memory");
}
__device__ __forceinline__ bool mbar_try(uint32_t bar, uint32_t parity) {
  uint32_t ok;
  asm volatile("{\n.reg .pred p;\nmbarrier.test_wait.parity.shared::cta.b64 p, [%1], %2;\nselp.u32 %0, 1, 0, p;\n}" : "=r"(ok) : "r"(bar), "r"(parity) : "memory");
  return ok;
}
__device__ __forceinline__ void mbar_wait(uint32_t bar, uint32_t parity) {
  asm volatile(
      "{\n.reg .pred p;\n.reg .u32 n;\nmov.u32 n, 0;\n"
      "W_LOOP:\nmbarrier.try_wait.parity.shared::cta.b64 p, [%0], %1;\n@p bra W_DONE;\n"
      "add.u32 n, n, 1;\nsetp.lt.u32 p, n, 0x40000;\n@p bra W_LOOP;\ntrap;\nW_DONE:\n}" ::"r"(bar), "r"(parity) : "memory");
}
__device__ __forceinline__ void bulk_load(uint32_t dst, const void* src, uint32_t bytes, uint32_t bar) {
  asm volatile("cp.async.bulk.shared::cluster.global.mbarrier::complete_tx::bytes [%0], [%1], %2, [%3];" ::"r"(dst), "l"(src), "r"(bytes), "r"(bar) : "memory");
}
__device__ __forceinline__ void cp16(uint32_t dst, const void* src) { asm volatile("cp.async.cg.shared.global [%0], [%1], 16;" ::"r"(dst), "l"(src) : "memory"); }
__device__ __forceinline__ void spin_guard(uint32_t t0) { if ((uint32_t)clock() - t0 > (1u << 30)) __trap(); }
__device__ __forceinline__ float tagf(float v, uint32_t tag) { return __uint_as_float((__float_as_uint(v) & ~1u) | tag); }
__device__ __forceinline__ float untag(float v) { return __uint_as_float(__float_as_uint(v) & ~1u); }
__device__ __forceinline__ void st_x2(float2* p, float a, float b) { asm volatile("st.relaxed.gpu.global.v2.f32 [%0], {%1,%2};" ::"l"(p), "f"(a), "f"(b) : "memory"); }
__device__ __forceinline__ float2 ld_x2(const float2* p) { float2 v; asm volatile("ld.relaxed.gpu.global.v2.f32 {%0,%1}, [%2];" : "=f"(v.x), "=f"(v.y) : "l"(p) : "memory"); return v; }
__device__ __forceinline__ void st_u2(uint2* p, uint32_t a, uint32_t b) { asm volatile("st.relaxed.gpu.global.v2.u32 [%0], {%1,%2};" ::"l"(p), "r"(a), "r"(b) : "memory"); }
__device__ __forceinline__ void prefetch2d(const CUtensorMap* m, int c0, int c1) { asm volatile("cp.async.bulk.prefetch.tensor.2d.L2.global [%0, {%1, %2}];" ::"l"(m), "r"(c0), "r"(c1) : "memory"); }
__device__ __forceinline__ void prefetch1d(const void* p, uint32_t bytes) { asm volatile("cp.async.bulk.prefetch.L2.global [%0], %1;" ::"l"(p), "r"(bytes) : "memory"); }
__device__ __forceinline__ uint32_t ld_x1(const void* p) { uint32_t v; asm volatile("ld.relaxed.gpu.global.u32 %0, [%1];" : "=r"(v) : "l"(p) : "memory"); return v; }
__device__ __forceinline__ uint4 ld_x4(const void* p) { uint4 v; asm volatile("ld.relaxed.gpu.global.v4.u32 {%0,%1,%2,%3}, [%4];" : "=r"(v.x), "=r"(v.y), "=r"(v.z), "=r"(v.w) : "l"(p) : "memory"); return v; }
__device__ __forceinline__ void st_x4(void* p, uint32_t a, uint32_t b, uint32_t c, uint32_t d) { asm volatile("st.relaxed.gpu.global.v4.u32 [%0], {%1,%2,%3,%4};" ::"l"(p), "r"(a), "r"(b), "r"(c), "r"(d) : "memory"); }
__device__ __forceinline__ uint32_t mapa(uint32_t a, uint32_t cta) { uint32_t r; asm volatile("mapa.shared::cluster.u32 %0, %1, %2;" : "=r"(r) : "r"(a), "r"(cta)); return r; }
__device__ __forceinline__ void stsm4t(uint32_t a, uint32_t r0, uint32_t r1, uint32_t r2, uint32_t r3) {
  asm volatile("stmatrix.sync.aligned.m8n8.x4.trans.shared.b16 [%0], {%1,%2,%3,%4};" ::"r"(a), "r"(r0), "r"(r1), "r"(r2), "r"(r3) : "memory");
}
__device__ __forceinline__ void hint_add(unsigned* p) { asm volatile("red.relaxed.gpu.global.add.u32 [%0], 1;" ::"l"(p) : "memory"); }
__device__ __forceinline__ void hint_wait(const unsigned* p, unsigned target) {
  const uint32_t t0 = (uint32_t)clock();
  while ((int)(ld_x1(p) - target) < 0) spin_guard(t0);
}
__device__ __forceinline__ void bulk_done_signal(unsigned* p) {
  asm volatile("cp.async.bulk.commit_group;\ncp.async.bulk.wait_group 0;\nfence.proxy.async.global;" ::: "memory");
  hint_add(p);
}
__device__ __forceinline__ void flag_wait(const unsigned* p, unsigned target) {
  hint_wait(p, target);
  asm volatile("fence.proxy.async.global;" ::: "memory");
}
__device__ __forceinline__ void tma2d(uint32_t dst, const CUtensorMap* m, uint32_t bar, int c0, int c1) {
  asm volatile("cp.async.bulk.tensor.2d.shared::cluster.global.mbarrier::complete_tx::bytes [%0], [%1, {%3, %4}], [%2];" ::"r"(dst), "l"(m), "r"(bar), "r"(c0), "r"(c1) : "memory");
}
__device__ __forceinline__ void tma3d(uint32_t dst, const CUtensorMap* m, uint32_t bar, int c0, int c1, int c2) {
  asm volatile("cp.async.bulk.tensor.3d.shared::cluster.global.mbarrier::complete_tx::bytes [%0], [%1, {%3, %4, %5}], [%2];" ::"r"(dst), "l"(m), "r"(bar), "r"(c0), "r"(c1), "r"(c2) : "memory");
}
__device__ __forceinline__ void tma4d(uint32_t dst, const CUtensorMap* m, uint32_t bar, int c0, int c1, int c2, int c3) {
  asm volatile("cp.async.bulk.tensor.4d.shared::cluster.global.mbarrier::complete_tx::bytes [%0], [%1, {%3, %4, %5, %6}], [%2];" ::"r"(dst), "l"(m), "r"(bar), "r"(c0), "r"(c1), "r"(c2), "r"(c3) : "memory");
}
__device__ __forceinline__ void wg_fence() { asm volatile("wgmma.fence.sync.aligned;" ::: "memory"); }
__device__ __forceinline__ void wg_commit() { asm volatile("wgmma.commit_group.sync.aligned;" ::: "memory"); }
template <int N> __device__ __forceinline__ void wg_wait() { asm volatile("wgmma.wait_group.sync.aligned %0;" ::"n"(N) : "memory"); }
template <int O, int N, int NN> __device__ __forceinline__ void fence_regs(float (&d)[NN]) {
#pragma unroll
  for (int i = 0; i < N; i++) asm volatile("" : "+f"(d[O + i])::"memory");
}
__device__ __forceinline__ uint32_t pack_bf16(float lo, float hi) {
  uint32_t r; asm("cvt.rn.bf16x2.f32 %0, %1, %2;" : "=r"(r) : "f"(hi), "f"(lo)); return r;
}
__device__ __forceinline__ uint32_t pack_pin(float lo, float hi) {
  uint32_t r; asm volatile("cvt.rn.bf16x2.f32 %0, %1, %2;" : "=r"(r) : "f"(hi), "f"(lo) : "memory"); return r;
}
__device__ __forceinline__ float bf_lo(uint32_t u) { return __uint_as_float(u << 16); }
__device__ __forceinline__ float bf_hi(uint32_t u) { return __uint_as_float(u & 0xffff0000u); }

__device__ __forceinline__ uint64_t d128(uint32_t lo) { uint64_t d; asm("mov.b64 %0, {%1, 0x40000040};" : "=l"(d) : "r"(lo)); return d; }
__device__ __forceinline__ uint64_t d64(uint32_t lo) { uint64_t d; asm("mov.b64 %0, {%1, 0x80000020};" : "=l"(d) : "r"(lo)); return d; }
template<int O,int TB,int ACC,int NN> __device__ __forceinline__ void mma_ss64(float (&d)[NN], uint64_t da, uint64_t db, int sd = 0){
  if constexpr (ACC == 1) asm volatile("wgmma.mma_async.sync.aligned.m64n64k16.f32.bf16.bf16 {%0,%1,%2,%3,%4,%5,%6,%7,%8,%9,%10,%11,%12,%13,%14,%15,%16,%17,%18,%19,%20,%21,%22,%23,%24,%25,%26,%27,%28,%29,%30,%31}, %32, %33, 1, 1, 1, %35, %34;"
   : "+f"(d[O+0]), "+f"(d[O+1]), "+f"(d[O+2]), "+f"(d[O+3]), "+f"(d[O+4]), "+f"(d[O+5]), "+f"(d[O+6]), "+f"(d[O+7]), "+f"(d[O+8]), "+f"(d[O+9]), "+f"(d[O+10]), "+f"(d[O+11]), "+f"(d[O+12]), "+f"(d[O+13]), "+f"(d[O+14]), "+f"(d[O+15]), "+f"(d[O+16]), "+f"(d[O+17]), "+f"(d[O+18]), "+f"(d[O+19]), "+f"(d[O+20]), "+f"(d[O+21]), "+f"(d[O+22]), "+f"(d[O+23]), "+f"(d[O+24]), "+f"(d[O+25]), "+f"(d[O+26]), "+f"(d[O+27]), "+f"(d[O+28]), "+f"(d[O+29]), "+f"(d[O+30]), "+f"(d[O+31])
   : "l"(da), "l"(db), "n"(TB & 1), "n"(TB >> 1));
  else if constexpr (ACC == 0) asm volatile("wgmma.mma_async.sync.aligned.m64n64k16.f32.bf16.bf16 {%0,%1,%2,%3,%4,%5,%6,%7,%8,%9,%10,%11,%12,%13,%14,%15,%16,%17,%18,%19,%20,%21,%22,%23,%24,%25,%26,%27,%28,%29,%30,%31}, %32, %33, 0, 1, 1, %35, %34;"
   : "=f"(d[O+0]), "=f"(d[O+1]), "=f"(d[O+2]), "=f"(d[O+3]), "=f"(d[O+4]), "=f"(d[O+5]), "=f"(d[O+6]), "=f"(d[O+7]), "=f"(d[O+8]), "=f"(d[O+9]), "=f"(d[O+10]), "=f"(d[O+11]), "=f"(d[O+12]), "=f"(d[O+13]), "=f"(d[O+14]), "=f"(d[O+15]), "=f"(d[O+16]), "=f"(d[O+17]), "=f"(d[O+18]), "=f"(d[O+19]), "=f"(d[O+20]), "=f"(d[O+21]), "=f"(d[O+22]), "=f"(d[O+23]), "=f"(d[O+24]), "=f"(d[O+25]), "=f"(d[O+26]), "=f"(d[O+27]), "=f"(d[O+28]), "=f"(d[O+29]), "=f"(d[O+30]), "=f"(d[O+31])
   : "l"(da), "l"(db), "n"(TB & 1), "n"(TB >> 1));
  else asm volatile("{\n.reg .pred p;\nsetp.ne.b32 p, %36, 0;\nwgmma.mma_async.sync.aligned.m64n64k16.f32.bf16.bf16 {%0,%1,%2,%3,%4,%5,%6,%7,%8,%9,%10,%11,%12,%13,%14,%15,%16,%17,%18,%19,%20,%21,%22,%23,%24,%25,%26,%27,%28,%29,%30,%31}, %32, %33, p, 1, 1, %35, %34;\n}"
   : "+f"(d[O+0]), "+f"(d[O+1]), "+f"(d[O+2]), "+f"(d[O+3]), "+f"(d[O+4]), "+f"(d[O+5]), "+f"(d[O+6]), "+f"(d[O+7]), "+f"(d[O+8]), "+f"(d[O+9]), "+f"(d[O+10]), "+f"(d[O+11]), "+f"(d[O+12]), "+f"(d[O+13]), "+f"(d[O+14]), "+f"(d[O+15]), "+f"(d[O+16]), "+f"(d[O+17]), "+f"(d[O+18]), "+f"(d[O+19]), "+f"(d[O+20]), "+f"(d[O+21]), "+f"(d[O+22]), "+f"(d[O+23]), "+f"(d[O+24]), "+f"(d[O+25]), "+f"(d[O+26]), "+f"(d[O+27]), "+f"(d[O+28]), "+f"(d[O+29]), "+f"(d[O+30]), "+f"(d[O+31])
   : "l"(da), "l"(db), "n"(TB & 1), "n"(TB >> 1), "r"(sd));
}
template<int O,int TB,int ACC,int NN> __device__ __forceinline__ void mma_rs64(float (&d)[NN], uint32_t a0, uint32_t a1, uint32_t a2, uint32_t a3, uint64_t db, int sd = 0){
  if constexpr (ACC == 1) asm volatile("wgmma.mma_async.sync.aligned.m64n64k16.f32.bf16.bf16 {%0,%1,%2,%3,%4,%5,%6,%7,%8,%9,%10,%11,%12,%13,%14,%15,%16,%17,%18,%19,%20,%21,%22,%23,%24,%25,%26,%27,%28,%29,%30,%31}, {%32,%33,%34,%35}, %36, 1, 1, 1, %37;"
   : "+f"(d[O+0]), "+f"(d[O+1]), "+f"(d[O+2]), "+f"(d[O+3]), "+f"(d[O+4]), "+f"(d[O+5]), "+f"(d[O+6]), "+f"(d[O+7]), "+f"(d[O+8]), "+f"(d[O+9]), "+f"(d[O+10]), "+f"(d[O+11]), "+f"(d[O+12]), "+f"(d[O+13]), "+f"(d[O+14]), "+f"(d[O+15]), "+f"(d[O+16]), "+f"(d[O+17]), "+f"(d[O+18]), "+f"(d[O+19]), "+f"(d[O+20]), "+f"(d[O+21]), "+f"(d[O+22]), "+f"(d[O+23]), "+f"(d[O+24]), "+f"(d[O+25]), "+f"(d[O+26]), "+f"(d[O+27]), "+f"(d[O+28]), "+f"(d[O+29]), "+f"(d[O+30]), "+f"(d[O+31])
   : "r"(a0), "r"(a1), "r"(a2), "r"(a3), "l"(db), "n"(TB));
  else if constexpr (ACC == 0) asm volatile("wgmma.mma_async.sync.aligned.m64n64k16.f32.bf16.bf16 {%0,%1,%2,%3,%4,%5,%6,%7,%8,%9,%10,%11,%12,%13,%14,%15,%16,%17,%18,%19,%20,%21,%22,%23,%24,%25,%26,%27,%28,%29,%30,%31}, {%32,%33,%34,%35}, %36, 0, 1, 1, %37;"
   : "=f"(d[O+0]), "=f"(d[O+1]), "=f"(d[O+2]), "=f"(d[O+3]), "=f"(d[O+4]), "=f"(d[O+5]), "=f"(d[O+6]), "=f"(d[O+7]), "=f"(d[O+8]), "=f"(d[O+9]), "=f"(d[O+10]), "=f"(d[O+11]), "=f"(d[O+12]), "=f"(d[O+13]), "=f"(d[O+14]), "=f"(d[O+15]), "=f"(d[O+16]), "=f"(d[O+17]), "=f"(d[O+18]), "=f"(d[O+19]), "=f"(d[O+20]), "=f"(d[O+21]), "=f"(d[O+22]), "=f"(d[O+23]), "=f"(d[O+24]), "=f"(d[O+25]), "=f"(d[O+26]), "=f"(d[O+27]), "=f"(d[O+28]), "=f"(d[O+29]), "=f"(d[O+30]), "=f"(d[O+31])
   : "r"(a0), "r"(a1), "r"(a2), "r"(a3), "l"(db), "n"(TB));
  else asm volatile("{\n.reg .pred p;\nsetp.ne.b32 p, %38, 0;\nwgmma.mma_async.sync.aligned.m64n64k16.f32.bf16.bf16 {%0,%1,%2,%3,%4,%5,%6,%7,%8,%9,%10,%11,%12,%13,%14,%15,%16,%17,%18,%19,%20,%21,%22,%23,%24,%25,%26,%27,%28,%29,%30,%31}, {%32,%33,%34,%35}, %36, p, 1, 1, %37;\n}"
   : "+f"(d[O+0]), "+f"(d[O+1]), "+f"(d[O+2]), "+f"(d[O+3]), "+f"(d[O+4]), "+f"(d[O+5]), "+f"(d[O+6]), "+f"(d[O+7]), "+f"(d[O+8]), "+f"(d[O+9]), "+f"(d[O+10]), "+f"(d[O+11]), "+f"(d[O+12]), "+f"(d[O+13]), "+f"(d[O+14]), "+f"(d[O+15]), "+f"(d[O+16]), "+f"(d[O+17]), "+f"(d[O+18]), "+f"(d[O+19]), "+f"(d[O+20]), "+f"(d[O+21]), "+f"(d[O+22]), "+f"(d[O+23]), "+f"(d[O+24]), "+f"(d[O+25]), "+f"(d[O+26]), "+f"(d[O+27]), "+f"(d[O+28]), "+f"(d[O+29]), "+f"(d[O+30]), "+f"(d[O+31])
   : "r"(a0), "r"(a1), "r"(a2), "r"(a3), "l"(db), "n"(TB), "r"(sd));
}
template<int O,int TB,int ACC,int NN> __device__ __forceinline__ void mma_ss128(float (&d)[NN], uint64_t da, uint64_t db, int sd = 0){
  if constexpr (ACC == 1) asm volatile("wgmma.mma_async.sync.aligned.m64n128k16.f32.bf16.bf16 {%0,%1,%2,%3,%4,%5,%6,%7,%8,%9,%10,%11,%12,%13,%14,%15,%16,%17,%18,%19,%20,%21,%22,%23,%24,%25,%26,%27,%28,%29,%30,%31,%32,%33,%34,%35,%36,%37,%38,%39,%40,%41,%42,%43,%44,%45,%46,%47,%48,%49,%50,%51,%52,%53,%54,%55,%56,%57,%58,%59,%60,%61,%62,%63}, %64, %65, 1, 1, 1, %67, %66;"
   : "+f"(d[O+0]), "+f"(d[O+1]), "+f"(d[O+2]), "+f"(d[O+3]), "+f"(d[O+4]), "+f"(d[O+5]), "+f"(d[O+6]), "+f"(d[O+7]), "+f"(d[O+8]), "+f"(d[O+9]), "+f"(d[O+10]), "+f"(d[O+11]), "+f"(d[O+12]), "+f"(d[O+13]), "+f"(d[O+14]), "+f"(d[O+15]), "+f"(d[O+16]), "+f"(d[O+17]), "+f"(d[O+18]), "+f"(d[O+19]), "+f"(d[O+20]), "+f"(d[O+21]), "+f"(d[O+22]), "+f"(d[O+23]), "+f"(d[O+24]), "+f"(d[O+25]), "+f"(d[O+26]), "+f"(d[O+27]), "+f"(d[O+28]), "+f"(d[O+29]), "+f"(d[O+30]), "+f"(d[O+31]), "+f"(d[O+32]), "+f"(d[O+33]), "+f"(d[O+34]), "+f"(d[O+35]), "+f"(d[O+36]), "+f"(d[O+37]), "+f"(d[O+38]), "+f"(d[O+39]), "+f"(d[O+40]), "+f"(d[O+41]), "+f"(d[O+42]), "+f"(d[O+43]), "+f"(d[O+44]), "+f"(d[O+45]), "+f"(d[O+46]), "+f"(d[O+47]), "+f"(d[O+48]), "+f"(d[O+49]), "+f"(d[O+50]), "+f"(d[O+51]), "+f"(d[O+52]), "+f"(d[O+53]), "+f"(d[O+54]), "+f"(d[O+55]), "+f"(d[O+56]), "+f"(d[O+57]), "+f"(d[O+58]), "+f"(d[O+59]), "+f"(d[O+60]), "+f"(d[O+61]), "+f"(d[O+62]), "+f"(d[O+63])
   : "l"(da), "l"(db), "n"(TB & 1), "n"(TB >> 1));
  else if constexpr (ACC == 0) asm volatile("wgmma.mma_async.sync.aligned.m64n128k16.f32.bf16.bf16 {%0,%1,%2,%3,%4,%5,%6,%7,%8,%9,%10,%11,%12,%13,%14,%15,%16,%17,%18,%19,%20,%21,%22,%23,%24,%25,%26,%27,%28,%29,%30,%31,%32,%33,%34,%35,%36,%37,%38,%39,%40,%41,%42,%43,%44,%45,%46,%47,%48,%49,%50,%51,%52,%53,%54,%55,%56,%57,%58,%59,%60,%61,%62,%63}, %64, %65, 0, 1, 1, %67, %66;"
   : "=f"(d[O+0]), "=f"(d[O+1]), "=f"(d[O+2]), "=f"(d[O+3]), "=f"(d[O+4]), "=f"(d[O+5]), "=f"(d[O+6]), "=f"(d[O+7]), "=f"(d[O+8]), "=f"(d[O+9]), "=f"(d[O+10]), "=f"(d[O+11]), "=f"(d[O+12]), "=f"(d[O+13]), "=f"(d[O+14]), "=f"(d[O+15]), "=f"(d[O+16]), "=f"(d[O+17]), "=f"(d[O+18]), "=f"(d[O+19]), "=f"(d[O+20]), "=f"(d[O+21]), "=f"(d[O+22]), "=f"(d[O+23]), "=f"(d[O+24]), "=f"(d[O+25]), "=f"(d[O+26]), "=f"(d[O+27]), "=f"(d[O+28]), "=f"(d[O+29]), "=f"(d[O+30]), "=f"(d[O+31]), "=f"(d[O+32]), "=f"(d[O+33]), "=f"(d[O+34]), "=f"(d[O+35]), "=f"(d[O+36]), "=f"(d[O+37]), "=f"(d[O+38]), "=f"(d[O+39]), "=f"(d[O+40]), "=f"(d[O+41]), "=f"(d[O+42]), "=f"(d[O+43]), "=f"(d[O+44]), "=f"(d[O+45]), "=f"(d[O+46]), "=f"(d[O+47]), "=f"(d[O+48]), "=f"(d[O+49]), "=f"(d[O+50]), "=f"(d[O+51]), "=f"(d[O+52]), "=f"(d[O+53]), "=f"(d[O+54]), "=f"(d[O+55]), "=f"(d[O+56]), "=f"(d[O+57]), "=f"(d[O+58]), "=f"(d[O+59]), "=f"(d[O+60]), "=f"(d[O+61]), "=f"(d[O+62]), "=f"(d[O+63])
   : "l"(da), "l"(db), "n"(TB & 1), "n"(TB >> 1));
  else asm volatile("{\n.reg .pred p;\nsetp.ne.b32 p, %68, 0;\nwgmma.mma_async.sync.aligned.m64n128k16.f32.bf16.bf16 {%0,%1,%2,%3,%4,%5,%6,%7,%8,%9,%10,%11,%12,%13,%14,%15,%16,%17,%18,%19,%20,%21,%22,%23,%24,%25,%26,%27,%28,%29,%30,%31,%32,%33,%34,%35,%36,%37,%38,%39,%40,%41,%42,%43,%44,%45,%46,%47,%48,%49,%50,%51,%52,%53,%54,%55,%56,%57,%58,%59,%60,%61,%62,%63}, %64, %65, p, 1, 1, %67, %66;\n}"
   : "+f"(d[O+0]), "+f"(d[O+1]), "+f"(d[O+2]), "+f"(d[O+3]), "+f"(d[O+4]), "+f"(d[O+5]), "+f"(d[O+6]), "+f"(d[O+7]), "+f"(d[O+8]), "+f"(d[O+9]), "+f"(d[O+10]), "+f"(d[O+11]), "+f"(d[O+12]), "+f"(d[O+13]), "+f"(d[O+14]), "+f"(d[O+15]), "+f"(d[O+16]), "+f"(d[O+17]), "+f"(d[O+18]), "+f"(d[O+19]), "+f"(d[O+20]), "+f"(d[O+21]), "+f"(d[O+22]), "+f"(d[O+23]), "+f"(d[O+24]), "+f"(d[O+25]), "+f"(d[O+26]), "+f"(d[O+27]), "+f"(d[O+28]), "+f"(d[O+29]), "+f"(d[O+30]), "+f"(d[O+31]), "+f"(d[O+32]), "+f"(d[O+33]), "+f"(d[O+34]), "+f"(d[O+35]), "+f"(d[O+36]), "+f"(d[O+37]), "+f"(d[O+38]), "+f"(d[O+39]), "+f"(d[O+40]), "+f"(d[O+41]), "+f"(d[O+42]), "+f"(d[O+43]), "+f"(d[O+44]), "+f"(d[O+45]), "+f"(d[O+46]), "+f"(d[O+47]), "+f"(d[O+48]), "+f"(d[O+49]), "+f"(d[O+50]), "+f"(d[O+51]), "+f"(d[O+52]), "+f"(d[O+53]), "+f"(d[O+54]), "+f"(d[O+55]), "+f"(d[O+56]), "+f"(d[O+57]), "+f"(d[O+58]), "+f"(d[O+59]), "+f"(d[O+60]), "+f"(d[O+61]), "+f"(d[O+62]), "+f"(d[O+63])
   : "l"(da), "l"(db), "n"(TB & 1), "n"(TB >> 1), "r"(sd));
}
template<int O,int TB,int ACC,int NN> __device__ __forceinline__ void mma_rs128(float (&d)[NN], uint32_t a0, uint32_t a1, uint32_t a2, uint32_t a3, uint64_t db, int sd = 0){
  if constexpr (ACC == 1) asm volatile("wgmma.mma_async.sync.aligned.m64n128k16.f32.bf16.bf16 {%0,%1,%2,%3,%4,%5,%6,%7,%8,%9,%10,%11,%12,%13,%14,%15,%16,%17,%18,%19,%20,%21,%22,%23,%24,%25,%26,%27,%28,%29,%30,%31,%32,%33,%34,%35,%36,%37,%38,%39,%40,%41,%42,%43,%44,%45,%46,%47,%48,%49,%50,%51,%52,%53,%54,%55,%56,%57,%58,%59,%60,%61,%62,%63}, {%64,%65,%66,%67}, %68, 1, 1, 1, %69;"
   : "+f"(d[O+0]), "+f"(d[O+1]), "+f"(d[O+2]), "+f"(d[O+3]), "+f"(d[O+4]), "+f"(d[O+5]), "+f"(d[O+6]), "+f"(d[O+7]), "+f"(d[O+8]), "+f"(d[O+9]), "+f"(d[O+10]), "+f"(d[O+11]), "+f"(d[O+12]), "+f"(d[O+13]), "+f"(d[O+14]), "+f"(d[O+15]), "+f"(d[O+16]), "+f"(d[O+17]), "+f"(d[O+18]), "+f"(d[O+19]), "+f"(d[O+20]), "+f"(d[O+21]), "+f"(d[O+22]), "+f"(d[O+23]), "+f"(d[O+24]), "+f"(d[O+25]), "+f"(d[O+26]), "+f"(d[O+27]), "+f"(d[O+28]), "+f"(d[O+29]), "+f"(d[O+30]), "+f"(d[O+31]), "+f"(d[O+32]), "+f"(d[O+33]), "+f"(d[O+34]), "+f"(d[O+35]), "+f"(d[O+36]), "+f"(d[O+37]), "+f"(d[O+38]), "+f"(d[O+39]), "+f"(d[O+40]), "+f"(d[O+41]), "+f"(d[O+42]), "+f"(d[O+43]), "+f"(d[O+44]), "+f"(d[O+45]), "+f"(d[O+46]), "+f"(d[O+47]), "+f"(d[O+48]), "+f"(d[O+49]), "+f"(d[O+50]), "+f"(d[O+51]), "+f"(d[O+52]), "+f"(d[O+53]), "+f"(d[O+54]), "+f"(d[O+55]), "+f"(d[O+56]), "+f"(d[O+57]), "+f"(d[O+58]), "+f"(d[O+59]), "+f"(d[O+60]), "+f"(d[O+61]), "+f"(d[O+62]), "+f"(d[O+63])
   : "r"(a0), "r"(a1), "r"(a2), "r"(a3), "l"(db), "n"(TB));
  else if constexpr (ACC == 0) asm volatile("wgmma.mma_async.sync.aligned.m64n128k16.f32.bf16.bf16 {%0,%1,%2,%3,%4,%5,%6,%7,%8,%9,%10,%11,%12,%13,%14,%15,%16,%17,%18,%19,%20,%21,%22,%23,%24,%25,%26,%27,%28,%29,%30,%31,%32,%33,%34,%35,%36,%37,%38,%39,%40,%41,%42,%43,%44,%45,%46,%47,%48,%49,%50,%51,%52,%53,%54,%55,%56,%57,%58,%59,%60,%61,%62,%63}, {%64,%65,%66,%67}, %68, 0, 1, 1, %69;"
   : "=f"(d[O+0]), "=f"(d[O+1]), "=f"(d[O+2]), "=f"(d[O+3]), "=f"(d[O+4]), "=f"(d[O+5]), "=f"(d[O+6]), "=f"(d[O+7]), "=f"(d[O+8]), "=f"(d[O+9]), "=f"(d[O+10]), "=f"(d[O+11]), "=f"(d[O+12]), "=f"(d[O+13]), "=f"(d[O+14]), "=f"(d[O+15]), "=f"(d[O+16]), "=f"(d[O+17]), "=f"(d[O+18]), "=f"(d[O+19]), "=f"(d[O+20]), "=f"(d[O+21]), "=f"(d[O+22]), "=f"(d[O+23]), "=f"(d[O+24]), "=f"(d[O+25]), "=f"(d[O+26]), "=f"(d[O+27]), "=f"(d[O+28]), "=f"(d[O+29]), "=f"(d[O+30]), "=f"(d[O+31]), "=f"(d[O+32]), "=f"(d[O+33]), "=f"(d[O+34]), "=f"(d[O+35]), "=f"(d[O+36]), "=f"(d[O+37]), "=f"(d[O+38]), "=f"(d[O+39]), "=f"(d[O+40]), "=f"(d[O+41]), "=f"(d[O+42]), "=f"(d[O+43]), "=f"(d[O+44]), "=f"(d[O+45]), "=f"(d[O+46]), "=f"(d[O+47]), "=f"(d[O+48]), "=f"(d[O+49]), "=f"(d[O+50]), "=f"(d[O+51]), "=f"(d[O+52]), "=f"(d[O+53]), "=f"(d[O+54]), "=f"(d[O+55]), "=f"(d[O+56]), "=f"(d[O+57]), "=f"(d[O+58]), "=f"(d[O+59]), "=f"(d[O+60]), "=f"(d[O+61]), "=f"(d[O+62]), "=f"(d[O+63])
   : "r"(a0), "r"(a1), "r"(a2), "r"(a3), "l"(db), "n"(TB));
  else asm volatile("{\n.reg .pred p;\nsetp.ne.b32 p, %70, 0;\nwgmma.mma_async.sync.aligned.m64n128k16.f32.bf16.bf16 {%0,%1,%2,%3,%4,%5,%6,%7,%8,%9,%10,%11,%12,%13,%14,%15,%16,%17,%18,%19,%20,%21,%22,%23,%24,%25,%26,%27,%28,%29,%30,%31,%32,%33,%34,%35,%36,%37,%38,%39,%40,%41,%42,%43,%44,%45,%46,%47,%48,%49,%50,%51,%52,%53,%54,%55,%56,%57,%58,%59,%60,%61,%62,%63}, {%64,%65,%66,%67}, %68, p, 1, 1, %69;\n}"
   : "+f"(d[O+0]), "+f"(d[O+1]), "+f"(d[O+2]), "+f"(d[O+3]), "+f"(d[O+4]), "+f"(d[O+5]), "+f"(d[O+6]), "+f"(d[O+7]), "+f"(d[O+8]), "+f"(d[O+9]), "+f"(d[O+10]), "+f"(d[O+11]), "+f"(d[O+12]), "+f"(d[O+13]), "+f"(d[O+14]), "+f"(d[O+15]), "+f"(d[O+16]), "+f"(d[O+17]), "+f"(d[O+18]), "+f"(d[O+19]), "+f"(d[O+20]), "+f"(d[O+21]), "+f"(d[O+22]), "+f"(d[O+23]), "+f"(d[O+24]), "+f"(d[O+25]), "+f"(d[O+26]), "+f"(d[O+27]), "+f"(d[O+28]), "+f"(d[O+29]), "+f"(d[O+30]), "+f"(d[O+31]), "+f"(d[O+32]), "+f"(d[O+33]), "+f"(d[O+34]), "+f"(d[O+35]), "+f"(d[O+36]), "+f"(d[O+37]), "+f"(d[O+38]), "+f"(d[O+39]), "+f"(d[O+40]), "+f"(d[O+41]), "+f"(d[O+42]), "+f"(d[O+43]), "+f"(d[O+44]), "+f"(d[O+45]), "+f"(d[O+46]), "+f"(d[O+47]), "+f"(d[O+48]), "+f"(d[O+49]), "+f"(d[O+50]), "+f"(d[O+51]), "+f"(d[O+52]), "+f"(d[O+53]), "+f"(d[O+54]), "+f"(d[O+55]), "+f"(d[O+56]), "+f"(d[O+57]), "+f"(d[O+58]), "+f"(d[O+59]), "+f"(d[O+60]), "+f"(d[O+61]), "+f"(d[O+62]), "+f"(d[O+63])
   : "r"(a0), "r"(a1), "r"(a2), "r"(a3), "l"(db), "n"(TB), "r"(sd));
}

#define NEARLY 0
#define XAHEAD 3
#define HEADN 6
#define WBATCH 1
#define NOLDS 2
#define NOSEND 0
#define MSPLIT 3
#define SPACE 0
#define WPF 1
#define WAFTER 7
#define WPACE 0
#define GATE_AT 4
#define TPACE 40
#define PFMODE 0
#define MAPMODE 0
template <int V> struct IC { static constexpr int value = V; };
struct Maps { CUtensorMap x, ft, g64, u64, e, wr, wi, xs, ts, t, g32, u32, d224; };

constexpr int NCTA = 130;
constexpr int U = 16384;
constexpr int TB = 36864;
constexpr int OFF_RING = 8 * U, OFF_Z = 9 * U, OFF_XB = 12 * U, OFF_T = 13 * U, OFF_D = OFF_T;
constexpr int OFF_BAR = 14 * U, OFF_SP = OFF_BAR + 512, OFF_G = OFF_SP + 1024 + 128;
constexpr int SMEM_BYTES = OFF_G + 512;
constexpr int B_FX = 0, B_FA = 8, B_FT = 12, B_Z = 16, B_W = 24, B_HX = 25, B_TL = 26, B_HP = 27, B_WR = 30, B_E0 = 34;
constexpr int B_EA = 35, B_ET = 39, B_PZ = 43, B_RDY = 45, B_FE = 46;
constexpr int B_T = 50, B_XS = 51, B_G = 53, NBAR = 54;
__host__ __device__ constexpr int rslot(int n) { return n & 3; }
__host__ __device__ constexpr int rpar(int n) { return (n >> 2) & 1; }

__global__ void __cluster_dims__(2, 1, 1) __launch_bounds__(512, 1)
fused_kernel(const __grid_constant__ Maps maps, const __nv_bfloat16* __restrict__ w_r,
             const __nv_bfloat16* __restrict__ w_i, const __nv_bfloat16* __restrict__ gate_w, __nv_bfloat16* __restrict__ out) {
  extern __shared__ __align__(1024) uint8_t smem[];
  const uint32_t sb = smem_u32(smem);
  const uint32_t bars = sb + OFF_BAR;
  const int tid = threadIdx.x, lane = tid & 31;
  const int warp = __shfl_sync(0xffffffffu, tid >> 5, 0);
  const bool helper = blockIdx.x >= 128;
  const int cl = (blockIdx.x >> 1) & 63, rank = blockIdx.x & 1;
  const int q4 = cl & 3, rb = cl >> 2;
  const int j = 2 * q4 + rank;
  const int f_full = 448 * q4 + (rank ? 256 : 0);
  const int f_half = 448 * q4 + (rank ? 224 : 192);
  const int kg = 2 * j + (rb >> 3), tn = rb & 7;

  if (tid == 64) { PROF_EV(0); PROF_CK(40); }
  if (warp < 8) {
    asm volatile("barrier.cluster.arrive.relaxed.aligned;" ::: "memory");
    asm volatile("setmaxnreg.inc.sync.aligned.u32 192;");
    if (!helper) {
      const int wg = warp >> 2, w = warp & 3, g = lane >> 2;
      const bool elect = (tid & 127) == 0;
      float cX[32], cA[64], cB[64], cC[64], ci[64], ct[64];
      const int zero = blockIdx.x >> 16;
      uint32_t h[56], yf[16];
      const uint32_t d0 = (sb & 0x3FFFF) >> 4;
      const uint32_t dK = d0 | (1u << 16), dN = d0 | (512u << 16);
      const uint32_t dX = dK + wg * 512;
      constexpr uint32_t RING = OFF_RING >> 4;
      auto waitA = [&](int n) { mbar_wait(bars + 8 * (B_FA + rslot(n)), rpar(n)); };
      auto freeA = [&](int n) { mbar_arrive_if(elect, bars + 8 * (B_EA + rslot(n))); };
      auto nop = [] {};

      asm volatile("bar.sync 0, 384;" ::: "memory");
#pragma unroll 1
      for (int i = 0; i < 4; i++) {
        const uint64_t dx = d128(dX + i * 2048), df = d128(dK + (OFF_XB >> 4) + (i & 1) * 1024);
        mbar_wait(bars + 8 * (B_FX + 2 * i), 0);
        wg_fence();
        mma_ss64<0, 0, 2>(cX, df, dx, i);
        mma_ss64<0, 0, 1>(cX, df + 2, dx + 2);
        wg_commit(); wg_wait<1>();
        mbar_arrive_if(elect && i, bars + 8 * (B_EA + rslot(i - 1)));
        mma_ss64<0, 0, 1>(cX, df + 4, dx + 4);
        mma_ss64<0, 0, 1>(cX, df + 6, dx + 6);
        if (i == 0 && tid == 0) PROF_EV(1);
        mbar_wait(bars + 8 * (B_FX + 2 * i + 1), 0);
        wg_fence();
#pragma unroll
        for (int k = 0; k < 4; k++) mma_ss64<0, 0, 1>(cX, df + (512 + k * 2), dx + (1024 + k * 2));
        wg_commit();
        waitA(i);
        wg_fence();
        const uint64_t da = d128(dX + i * 1024), db = d128(dN + RING + i * 1024);
        mma_ss128<0, 1, 2>(cA, da, db, i);
        wg_commit(); wg_wait<1>();
        mbar_arrive_if(elect, bars + 8 * (B_FE + i));
#pragma unroll
        for (int k = 1; k < 4; k++) mma_ss128<0, 1, 1>(cA, da + k * 2, db + k * 128);
        wg_commit();
      }
      fence_regs<0, 32>(cX);
#pragma unroll
      for (int e = 0; e < 16; e++) yf[e] = pack_pin(cX[2 * e], cX[2 * e + 1]);
      if (tid == 0) PROF_EV(2);
      {
        waitA(4); mbar_wait(bars + 8 * B_E0, 0);
        const uint64_t de = d128(dN + (wg ? RING : OFF_XB >> 4));
        wg_fence();
        mma_rs128<0, 1, 0>(cB, yf[0], yf[1], yf[2], yf[3], de);
        wg_commit();
        wg_wait<1>();
        freeA(3);
#pragma unroll
        for (int k = 1; k < 4; k++) mma_rs128<0, 1, 1>(cB, yf[4 * k], yf[4 * k + 1], yf[4 * k + 2], yf[4 * k + 3], de + k * 128);
        wg_commit();
      }
      bool rel = false;
      auto acquire = [&](int n) {
        rel = elect;
        if (!mbar_try(bars + 8 * (B_FA + rslot(n)), rpar(n))) { wg_wait<0>(); freeA(n - 1); rel = false; waitA(n); }
      };
      auto freeP = [&](int n) { mbar_arrive_if(rel, bars + 8 * (B_EA + rslot(n - 1))); };
      auto ffn_step = [&](auto first, auto split, float (&acc)[64], int n, int kb, auto done, auto work) {
        constexpr int SPLIT = decltype(split)::value;
        acquire(n);
        wg_fence();
        const uint64_t dx = d128(dX + kb * 1024), db = d128(dN + RING + rslot(n) * 1024);
        mma_ss128<0, 1, decltype(first)::value>(acc, dx, db, kb);
#pragma unroll
        for (int k = 1; k < SPLIT; k++) mma_ss128<0, 1, 1>(acc, dx + k * 2, db + k * 128);
        wg_commit();
        work();
        wg_wait<1>();
        freeP(n);
        done();
        if (SPLIT < 4) {
          wg_fence();
#pragma unroll
          for (int k = SPLIT; k < 4; k++) mma_ss128<0, 1, 1>(acc, dx + k * 2, db + k * 128);
          wg_commit();
        }
      };
      {
        const int s0 = 2 * rb + wg, kr = 2 * ((s0 & 1) | ((s0 & 4) >> 1));
        const int m = lane >> 3, r = lane & 7;
        const uint32_t a0 = sb + OFF_XB + wg * 8192 + (((w >> 1) * 8 + (m >> 1)) * 2 + (w & 1)) * 256 + (m & 1) * 128 + ((r ^ (kr + (m & 1))) << 4);
        ffn_step(IC<1>(), IC<4>(), cA, 5, 4, [&] { fence_regs<0, 64>(cB); }, nop);
        asm volatile("bar.sync 5, 256;" ::: "memory");
#pragma unroll
        for (int i = 0; i < 4; i++)
          stsm4t(a0 + i * 1024, pack_bf16(cB[8 * i] - cB[34 + 8 * i], cB[8 * i + 1] - cB[35 + 8 * i]),
                 pack_bf16(cB[32 + 8 * i] + cB[8 * i + 2], cB[33 + 8 * i] + cB[8 * i + 3]),
                 pack_bf16(cB[8 * i + 4] - cB[38 + 8 * i], cB[8 * i + 5] - cB[39 + 8 * i]),
                 pack_bf16(cB[36 + 8 * i] + cB[8 * i + 6], cB[37 + 8 * i] + cB[8 * i + 7]));
        if (j == 0 && w == 0) {
          const uint32_t a1 = r ? sb + OFF_SP + 1024 : sb + OFF_SP + wg * 512 + (m & 1) * 256 + (m >> 1) * 128;
#pragma unroll
          for (int n = 0; n < 8; n++)
            asm volatile("stmatrix.sync.aligned.m8n8.x4.shared.b16 [%0], {%1,%2,%3,%4};" ::"r"(a1 + ((n ^ (kr + (m >> 1))) << 4)),
                         "r"(pack_bf16(cB[4 * n], cB[4 * n + 1])), "r"(pack_bf16(cB[4 * n + 2], cB[4 * n + 3])),
                         "r"(pack_bf16(cB[32 + 4 * n], cB[33 + 4 * n])), "r"(pack_bf16(cB[34 + 4 * n], cB[35 + 4 * n])) : "memory");
        }
        ffn_step(IC<1>(), IC<2>(), cA, 6, 5, nop, [&] {
          asm volatile("fence.proxy.async.shared::cta;" ::: "memory");
          __syncwarp();
          mbar_arrive_if(lane == 0, bars + 8 * (B_XS + wg));
          if (tid == 0) PROF_EV(3);
        });
      }
#pragma unroll 1
      for (int kb = 6; kb < 8; kb++) ffn_step(IC<1>(), IC<1>(), cA, 1 + kb, kb, nop, nop);
      float g0 = 0.f, g1 = 0.f;
      uint32_t tag = 0;
      auto glu = [&](auto& acc, int half, int ho, int i0, int i1) {
#pragma unroll
        for (int i = i0; i < i1; i++) {
          const float o = 1.0f - ((i & 1) ? g1 : g0);
          asm volatile("" : "+f"(acc[2 * i]), "+f"(acc[2 * i + 1]), "+f"(acc[half + 2 * i]), "+f"(acc[half + 1 + 2 * i])::"memory");
          h[ho + i] = pack_pin(fmaxf(acc[2 * i], 0.f) * acc[half + 2 * i] * o, fmaxf(acc[2 * i + 1], 0.f) * acc[half + 1 + 2 * i] * o);
        }
      };
      ffn_step(IC<2>(), IC<1>(), cB, 9, zero, nop, nop);
#pragma unroll 1
      for (int kb = 1; kb < 8; kb++)
        ffn_step(IC<1>(), IC<1>(), cB, 9 + kb, kb, nop, [&] {
          if (kb == 4 + wg) {
            mbar_wait(bars + 8 * B_G, 0);
            const uint32_t gb0 = *(const uint32_t*)(smem + OFF_G + (wg * 64 + w * 16 + g) * 4), gb1 = *(const uint32_t*)(smem + OFF_G + (wg * 64 + w * 16 + g + 8) * 4);
            tag = gb0 & 1; g0 = __uint_as_float(gb0 & ~1u); g1 = __uint_as_float(gb1 & ~1u);
            glu(cA, 32, 0, 0, 8);
          } else if (kb == 6 + wg) glu(cA, 32, 0, 8, 16);
        });
      if (tid == 0) PROF_EV(4);
      ffn_step(IC<0>(), IC<1>(), cC, 17, 0, nop, nop);
#pragma unroll 1
      for (int kb = 1; kb < 8; kb++)
        ffn_step(IC<1>(), IC<1>(), cC, 17 + kb, kb, nop, [&] {
          if (kb == 1 + wg) glu(cB, 32, 16, 0, 8);
          else if (kb == 3 + wg) glu(cB, 32, 16, 8, 16);
        });
      if (tid == 0) PROF_EV(5);
      auto m_step = [&](auto first, int i) {
        acquire(25 + i);
        wg_fence();
        const uint64_t dx = d128(dX + i * 2048), dm = d64(dN + RING + rslot(25 + i) * 1024);
        mma_ss64<0, 1, decltype(first)::value>(ct, dx, dm);
#pragma unroll
        for (int k = 1; k < MSPLIT; k++) mma_ss64<0, 1, 1>(ct, dx + ((k >> 2) * 1024 + (k & 3) * 2), dm + k * 64);
        wg_commit();
        wg_wait<1>();
        mbar_arrive_if(rel && i < 3, bars + 8 * (B_EA + rslot(24 + i)));
        mbar_arrive_if(elect && i, bars + 8 * (B_ET + i - 1));
        wg_fence();
#pragma unroll
        for (int k = MSPLIT; k < 8; k++) mma_ss64<0, 1, 1>(ct, dx + ((k >> 2) * 1024 + (k & 3) * 2), dm + k * 64);
        wg_commit();
      };
      auto freeT = [&](int t) { mbar_arrive_if(elect, bars + 8 * (B_ET + t)); };
      m_step(IC<0>(), 0);
#pragma unroll 1
      for (int i = 1; i < 5; i++) {
        if (i == 1 + wg) glu(cC, 32, 32, 0, 8);
        else if (i == 3 + wg) glu(cC, 32, 32, 8, 16);
        if (i < 4) m_step(IC<1>(), i);
      }
      waitA(29 + wg);
      if (tid == 0) PROF_EV(6);
      if (tid == 128) PROF_EV(27);
      mbar_wait(bars + 8 * (j == 0 ? B_T : B_TL), 0);
      if (tid == 0) PROF_EV(7);
      wg_fence();
      {
        const uint64_t dt = d128(dN + (OFF_T >> 4) + wg * 512), de = d128(dK + RING + (1 + wg) * 1024);
        mma_ss64<0, 1, 0>(ci, de, dt);
        mma_ss64<32, 1, 0>(ci, de + 512, dt);
#pragma unroll
        for (int k = 1; k < 4; k++) {
          mma_ss64<0, 1, 1>(ci, de + k * 2, dt + k * 128);
          mma_ss64<32, 1, 1>(ci, de + (512 + k * 2), dt + k * 128);
        }
        wg_commit();
        wg_wait<1>();
        freeT(3);
        fence_regs<0, 32>(ct);
        glu(ct, 16, 48, 0, 8);
      }

      auto twait = [&](uint32_t bar, uint32_t par, int) { mbar_wait(bar, par); };
      auto fetch = [&](uint4 (&pv)[4], int z) {
        twait(bars + 8 * (z < 4 ? B_Z + 2 * z + wg : B_HP + z - 4), 0, 8 + z);
        const uint8_t* src = smem + (z < 4 ? OFF_Z + z * U : (z - 4) * U) + tid * 16;
#pragma unroll
        for (int i = 0; i < 4; i++) pv[i] = *(const uint4*)(src + i * 4096);
      };
      auto check = [&](uint4 (&pv)[4], int z) {
        const uint32_t t0 = (uint32_t)clock();
        while (__any_sync(0xffffffffu, ((pv[0].x ^ tag) | (pv[1].x ^ tag) | (pv[2].x ^ tag) | (pv[3].x ^ tag)) & 1)) {
#pragma unroll
          for (int i = 0; i < 4; i++) pv[i] = ld_x4(g_part + (size_t)((rb * 8 + j) * 3 + z - 4) * 1024 + tid + i * 256);
          spin_guard(t0);
        }
#pragma unroll
        for (int i = 0; i < 4; i++) pv[i].x &= ~1u;
      };
      auto head = [&](auto off, int t, bool init) {
        constexpr int O = decltype(off)::value;
        twait(bars + 8 * (B_FT + (t & 3)), t >> 2, t);
        const uint64_t db = d128(dN + (t & 3) * (TB >> 4) + rank * 256);
        wg_fence();
        mma_rs64<O, 1, 2>(ct, h[0], h[1], h[2], h[3], db, zero + init);
#pragma unroll
        for (int k = 1; k < 6; k++) mma_rs64<O, 1, 1>(ct, h[4 * k], h[4 * k + 1], h[4 * k + 2], h[4 * k + 3], db + k * 128);
        wg_commit();
        wg_wait<1>();
      };
      auto rest = [&](auto off, int t, int z) {
        constexpr int O = decltype(off)::value, P = 32 - O;
        const uint64_t db = d128(dN + (t & 3) * (TB >> 4)), dw = db + rank * 256, dm = db + (rank ? 0 : 1536);
        wg_fence();
#pragma unroll
        for (int k = 6; k < 12; k++) mma_rs64<O, 1, 1>(ct, h[4 * k], h[4 * k + 1], h[4 * k + 2], h[4 * k + 3], dw + k * 128);
        wg_commit();
        uint4 pv[4];
        if (z >= 0) fetch(pv, z);
        wg_fence();
#pragma unroll
        for (int k = 0; k < 2; k++) mma_rs64<O, 1, 1>(ct, h[48 + 4 * k], h[49 + 4 * k], h[50 + 4 * k], h[51 + 4 * k], dm + k * 128);
#pragma unroll
        for (int k = 0; k < 4; k++) mma_rs64<O, 1, 1>(ct, yf[4 * k], yf[4 * k + 1], yf[4 * k + 2], yf[4 * k + 3], db + (14 + k) * 128);
        wg_commit();
        if (z >= 0) {
          if (z >= 4) check(pv, z);
#pragma unroll
          for (int i = 0; i < 4; i++) {
            const uint32_t a[4] = {pv[i].x, pv[i].y, pv[i].z, pv[i].w};
#pragma unroll
            for (int e = 0; e < 4; e++) { ct[P + 8 * i + 2 * e] = bf_lo(a[e]); ct[P + 8 * i + 2 * e + 1] = bf_hi(a[e]); }
          }
        }
      };
      const uint32_t peerZ = mapa(sb + OFF_Z + tid * 16, rank ^ 1), peerB = mapa(bars + 8 * (B_Z + wg), rank ^ 1);
      auto send = [&](auto off, int t) {
        constexpr int O = decltype(off)::value;
        fence_regs<O, 32>(ct);
        const bool grid = t >= 3 && t < 6;
        const int z = grid ? t - 3 : t == 6 ? 3 : t;
        uint32_t pk[16];
#pragma unroll
        for (int i = 0; i < 16; i++) pk[i] = pack_bf16(ct[O + 2 * i], ct[O + 2 * i + 1]);
        if (grid) {
          const int owner = rb * 8 + 2 * ((q4 + z + 1) & 3) + rank;
          uint4* dst = g_part + (size_t)(owner * 3 + z) * 1024 + tid;
#pragma unroll
          for (int i = 0; i < 4; i++) st_x4(dst + i * 256, (pk[4 * i] & ~1u) | tag, pk[4 * i + 1], pk[4 * i + 2], pk[4 * i + 3]);
          __syncwarp();
          hint_add_if(lane == 0, &g_cntP[32 * owner + z]);
        } else {
#pragma unroll
          for (int i = 0; i < 4; i++)
            asm volatile("st.async.weak.shared::cluster.mbarrier::complete_tx::bytes.v4.b32 [%0], {%1,%2,%3,%4}, [%5];" ::"r"(peerZ + z * U + i * 4096),
                         "r"(pk[4 * i]), "r"(pk[4 * i + 1]), "r"(pk[4 * i + 2]), "r"(pk[4 * i + 3]), "r"(peerB + 16 * z) : "memory");
        }
      };
      asm volatile("barrier.cluster.wait.aligned;" ::: "memory");
      head(IC<0>(), 0, false);
      if (elect) asm volatile("mbarrier.arrive.shared::cluster.b64 _, [%0];" ::"r"(mapa(bars + 8 * B_RDY, rank ^ 1)) : "memory");
      fence_regs<0, 64>(ci);
#pragma unroll
      for (int i = 0; i < 16; i++) {
        const float gg = ((i & 1) ? g1 : g0) * (2.0f / (2048.0f * 512.0f));
        if (i & 2) yf[i] = pack_pin((ci[2 * i] - ci[28 + 2 * i]) * gg, (ci[2 * i + 1] - ci[29 + 2 * i]) * gg);
        else yf[i] = pack_pin((ci[2 * i] + ci[36 + 2 * i]) * gg, (ci[2 * i + 1] + ci[37 + 2 * i]) * gg);
      }
      if (tid == 0) PROF_EV(8);
      if (tid == 128) PROF_EV(28);
#pragma unroll 1
      for (int t = 0;; t += 2) {
        rest(IC<0>(), t, t - 2);
        head(IC<32>(), t + 1, t >= 2);
        mbar_arrive_if(elect && t < 6, bars + 8 * (B_ET + t));
        if (t == 0) twait(bars + 8 * B_RDY, 0, 15);
        send(IC<0>(), t);
        rest(IC<32>(), t + 1, (t & 2) ? t - 1 : -1);
        if (t == 6) break;
        head(IC<0>(), t + 2, t == 2);
        mbar_arrive_if(elect, bars + 8 * (B_ET + t + 1));
        send(IC<32>(), t + 1);
      }
      if (tid == 0) PROF_EV(9);
      if (tid == 128) PROF_EV(29);
      {
        float (&sum)[64] = ct;
        uint4 p2[4], p3[4];
        fetch(p3, 3);
        if (tid == 0) PROF_EV(25);
        fetch(p2, 6);
        if (tid == 0) PROF_EV(24);
        check(p2, 6);
#pragma unroll
        for (int i = 0; i < 4; i++) {
          const uint32_t b[4] = {p2[i].x, p2[i].y, p2[i].z, p2[i].w}, c[4] = {p3[i].x, p3[i].y, p3[i].z, p3[i].w};
#pragma unroll
          for (int e = 0; e < 4; e++) {
            sum[8 * i + 2 * e] += bf_lo(c[e]) + bf_lo(b[e]);
            sum[8 * i + 2 * e + 1] += bf_hi(c[e]) + bf_hi(b[e]);
          }
        }
        if (tid == 0) PROF_EV(14);
        wg_wait<0>();
        fence_regs<32, 32>(ct);
#pragma unroll
        for (int i = 0; i < 32; i++) sum[i] += ct[32 + i];
        const uint32_t stg = sb + OFF_T + warp * 2048;
        const int mr = (lane & 7) + ((lane >> 3) & 1) * 8, mc = lane >> 4;
#pragma unroll
        for (int i = 0; i < 4; i++) {
          const uint32_t a = stg + mr * 128 + (((2 * i + mc) ^ (mr & 7)) << 4);
          asm volatile("stmatrix.sync.aligned.m8n8.x4.shared.b16 [%0], {%1,%2,%3,%4};" ::"r"(a), "r"(pack_bf16(sum[8 * i], sum[8 * i + 1])),
                       "r"(pack_bf16(sum[8 * i + 2], sum[8 * i + 3])), "r"(pack_bf16(sum[8 * i + 4], sum[8 * i + 5])),
                       "r"(pack_bf16(sum[8 * i + 6], sum[8 * i + 7])) : "memory");
        }
        __syncwarp();
#pragma unroll
        for (int i = 0; i < 4; i++) {
          const int r = 4 * i + (lane >> 3), c = lane & 7;
          const uint4 v = *(const uint4*)(smem + OFF_T + warp * 2048 + r * 128 + ((c ^ (r & 7)) << 4));
          *(uint4*)(out + (size_t)(2 * rb + wg + 32 * (16 * w + r)) * 512 + 64 * j + 8 * c) = v;
        }
      }
      if (tid == 0) { PROF_EV(15); PROF_CK(41); }
      if (tid == 128) PROF_EV(30);
    }
  } else if (warp < 12) {
    asm volatile("setmaxnreg.dec.sync.aligned.u32 104;");
    asm volatile("barrier.cluster.arrive.relaxed.aligned;" ::: "memory");
    const int t = tid - 256, w = warp - 8;
    const uint32_t ep = ld_x1(&g_epoch[blockIdx.x * 8]);
    const uint32_t tag = (ep + 1) & 1;
    auto w_issue = [&](const CUtensorMap* m) {
          if (elect_one()) { mbar_expect_tx(bars + 8 * (B_WR + w), 3072); tma4d(sb + OFF_T + w * 3072, m, bars + 8 * (B_WR + w), 16 * kg, 0, 2 * w, tn); }
          __syncwarp();
    };
    auto gate_rows = [&] {
      const int r = 16 * j + 4 * w + (lane >> 3);
      const uint4* pg = (const uint4*)gate_w + (lane & 7);
      {
        float a = 0.f;
        asm volatile("bar.sync 4, 256;" ::: "memory");
#pragma unroll 1
        for (int hf = 0; hf < 2; hf++) {
          uint4 v[4], u[4];
#pragma unroll
          for (int kb = 0; kb < 4; kb++) v[kb] = __ldg(pg + (4 * hf + kb) * 8);
          mbar_wait(bars + 8 * (B_FE + 1 + 2 * hf), 0);
          if (hf) w_issue(&maps.wr);
#pragma unroll
          for (int kb = 0; kb < 4; kb++) u[kb] = *(const uint4*)(smem + (4 * hf + kb) * U + r * 128 + (((lane ^ r) & 7) << 4));
#pragma unroll
          for (int kb = 0; kb < 4; kb++) {
            a = fmaf(bf_lo(u[kb].x), bf_lo(v[kb].x), a); a = fmaf(bf_hi(u[kb].x), bf_hi(v[kb].x), a);
            a = fmaf(bf_lo(u[kb].y), bf_lo(v[kb].y), a); a = fmaf(bf_hi(u[kb].y), bf_hi(v[kb].y), a);
            a = fmaf(bf_lo(u[kb].z), bf_lo(v[kb].z), a); a = fmaf(bf_hi(u[kb].z), bf_hi(v[kb].z), a);
            a = fmaf(bf_lo(u[kb].w), bf_lo(v[kb].w), a); a = fmaf(bf_hi(u[kb].w), bf_hi(v[kb].w), a);
          }
        }
#pragma unroll
        for (int o = 4; o; o >>= 1) a += __shfl_xor_sync(0xffffffffu, a, o);
        if ((lane & 7) == 0)
          asm volatile("st.relaxed.gpu.global.f32 [%0], %1;" ::"l"(g_gate + rb * 128 + r), "f"(tagf(__fdividef(1.0f, 1.0f + __expf(-a)), tag)) : "memory");
        if (t == 0) PROF_EV(18);
      }
    };
    {
      const int g = lane >> 2, q = lane & 3;
      uint32_t wf[32];
      if (!helper) {
        gate_rows();
        const uint32_t wa = sb + OFF_T + w * (3072 + 4) + q * 48 + g * 2;
#pragma unroll 1
        for (int ri = 0; ri < 2; ri++) {
          mbar_wait(bars + 8 * (B_WR + w), ri);
#pragma unroll
          for (int n2 = 0; n2 < NOLDS; n2++) {
            uint32_t v[16];
#pragma unroll
            for (int i = 0; i < 16; i++)
              asm volatile("ld.shared.u16 %0, [%1];" : "=r"(v[i]) : "r"(wa + (4 * n2 + ((i >> 1) & 3)) * 192 + (i & 1) * (1536 + 2) + (i >> 3) * 16) : "memory");
#pragma unroll
            for (int i = 0; i < 16; i++) {
              uint32_t& d = wf[(i >> 3) * 16 + 8 * n2 + (i & 7)];
              d = __byte_perm(d, v[i], 0x5432);
              asm volatile("" : "+r"(d)::"memory");
            }
          }
          __syncwarp();
          if (ri == 0) w_issue(&maps.wi);
        }
        asm volatile("bar.sync 1, 128;" ::: "memory");
        if (t == 0) PROF_EV(11);
      } else {
        asm volatile("bar.sync 4, 256;" ::: "memory");
        hint_wait(&g_cntW[0], (ep + 1) * 128u);
        const uint32_t t0 = (uint32_t)clock();
#pragma unroll 1
        for (;;) {
          uint32_t bad = 0;
#pragma unroll
          for (int i = 0; i < 32; i++) {
            const float2 v = ld_x2((const float2*)g_Wh + (i >> 4) * 2048 + 16 * w + g + 8 * (i & 1) + 64 * q + ((i >> 1) & 7) * 256);
            wf[i] = __float_as_uint(v.x); bad |= __float_as_uint(v.y) ^ tag;
          }
          if (!__any_sync(0xffffffffu, bad & 1)) break;
          spin_guard(t0);
        }
        if (t == 0) PROF_EV(11);
      }
      if (w == 0 && elect_one()) { mbar_expect_tx(bars + 8 * B_W, 8192); bulk_load(sb + OFF_D, g_DT.v, 8192, bars + 8 * B_W); }
      if (!helper) {
        const uint32_t t0 = (uint32_t)clock();
        uint32_t v;
        do { v = ld_x1(g_gate + rb * 128 + t); spin_guard(t0); } while (__any_sync(0xffffffffu, (v ^ tag) & 1));
        *(uint32_t*)(smem + OFF_G + t * 4) = v;
        __syncwarp();
        mbar_arrive_if(lane == 0, bars + 8 * B_G);
      }
      mbar_wait(bars + 8 * B_W, 0);
      mbar_wait(bars + 8 * B_HX, 0);
      if (t == 0) PROF_EV(12);
      const uint32_t dd = (sb & 0x3FFFF) >> 4;
      const uint64_t dF = d128((dd + (OFF_D >> 4)) | (512u << 16)), dI = d128((dd + (OFF_D >> 4)) | (1u << 16)), dA = d128((dd + (OFF_XB >> 4)) | (512u << 16));
      float az[32];
      const int zero = blockIdx.x >> 16;
      uint32_t pf[32];
#pragma unroll
      for (int mt = 0; mt < 2; mt++) {
        wg_fence();
        if (mt == 0) mma_ss64<0, 3, 0>(az, dA, dF);
        else mma_ss64<0, 3, 2>(az, dA + 512, dF, zero);
#pragma unroll
        for (int k = 1; k < 4; k++) mma_ss64<0, 3, 1>(az, dA + (mt * 512 + k * 128), dF + k * 128);
        wg_commit();
        wg_wait<0>();
        fence_regs<0, 32>(az);
#pragma unroll
        for (int i = 0; i < 16; i++) {
          const float wr = bf_lo(wf[16 * mt + i]), wi = bf_hi(wf[16 * mt + i]);
          pf[16 * mt + i] = pack_pin(fmaf(az[2 * i], wr, -az[2 * i + 1] * wi), fmaf(az[2 * i], wi, az[2 * i + 1] * wr));
        }
      }
      if (t == 0) PROF_EV(16);
#pragma unroll
      for (int mt = 0; mt < 2; mt++) {
        wg_fence();
        mma_rs64<0, 0, 2>(az, pf[16 * mt], pf[16 * mt + 1], pf[16 * mt + 2], pf[16 * mt + 3], dI, mt ? (int)helper : zero);
#pragma unroll
        for (int k = 1; k < 4; k++) mma_rs64<0, 0, 1>(az, pf[16 * mt + 4 * k], pf[16 * mt + 4 * k + 1], pf[16 * mt + 4 * k + 2], pf[16 * mt + 4 * k + 3], dI + k * 2);
        wg_commit();
        wg_wait<0>();
        fence_regs<0, 32>(az);
        if (!helper) {
          const int m = lane >> 3, r = lane & 7;
          const int sl = 2 * (m >> 1) + ((r >> 1) & 1) + 4 * (r >> 2);
          const uint32_t a0 = sb + OFF_XB + (2 * w + (m & 1)) * 2048 + sl * 64 + (((mt * 2 + (r & 1)) ^ (sl >> 1)) << 4);
#pragma unroll
          for (int i = 0; i < 4; i++)
            stsm4t(a0 + i * 512, pack_bf16(az[8 * i], az[8 * i + 1]), pack_bf16(az[8 * i + 2], az[8 * i + 3]), pack_bf16(az[8 * i + 4], az[8 * i + 5]),
                   pack_bf16(az[8 * i + 6], az[8 * i + 7]));
        }
      }
      if (helper) {
#pragma unroll
        for (int i = 0; i < 16; i++) {
          const int n = i >> 1, s0 = 8 * (n >> 1) + 2 * (n & 1) + (q & 1) + 4 * (q >> 1);
          if ((n & 1) == (int)(blockIdx.x & 1)) st_u2(g_Ts + s0 * 64 + 16 * w + g + 8 * (i & 1), pack_bf16(az[2 * i], az[2 * i + 1]), tag);
        }
        __syncwarp();
        hint_add_if(lane == 0, &g_cntH[0]);
        if (t == 0) { g_epoch[blockIdx.x * 8] = ep + 1; PROF_EV(13); }
      } else {
        asm volatile("fence.proxy.async.shared::cta;" ::: "memory");
        __syncwarp();
        if (elect_one()) {
          if (t == 0) PROF_EV(17);
          if (SPACE) __nanosleep(SPACE * w);
          asm volatile("cp.async.bulk.tensor.3d.global.shared::cta.bulk_group [%0, {%2, %3, %4}], [%1];" ::"l"(&maps.ts), "r"(sb + OFF_XB + w * 4096),
                       "r"(32 * kg), "r"(0), "r"(8 * tn + 2 * w) : "memory");
          bulk_done_signal(&g_cntT[32 * j]);
          if (t == 96) PROF_EV(13);
        }
        __syncwarp();
        if (j == 0) {
          hint_wait(&g_cntH[0], (ep + 1) * 8u);
          const uint32_t t0 = (uint32_t)clock();
          float2 v;
          do { v = ld_x2((const float2*)g_Ts + 2 * rb * 64 + t); spin_guard(t0); } while (__any_sync(0xffffffffu, (__float_as_uint(v.y) ^ tag) & 1));
          mbar_wait(bars + 8 * B_TL, 0);
          const uint32_t u = __float_as_uint(v.x);
          *(uint16_t*)(smem + OFF_T + t * 128 + ((t & 7) << 4)) = (uint16_t)u;
          *(uint16_t*)(smem + OFF_T + t * 128 + (((t & 7) ^ 1) << 4)) = (uint16_t)(u >> 16);
          asm volatile("fence.proxy.async.shared::cta;" ::: "memory");
          __syncwarp();
          mbar_arrive_if(lane == 0, bars + 8 * B_T);
        }
      }
    }
  } else {
    asm volatile("setmaxnreg.dec.sync.aligned.u32 24;");
    auto xf_load = [&](int q) {
      const uint32_t fb = bars + 8 * (B_FX + q);
      mbar_expect_tx(fb, U + 8192);
      tma3d(sb + q * U, &maps.x, fb, 64 * q, 0, 2 * rb);
      if (q >= 4) mbar_wait(bars + 8 * (B_FE + ((q - 4) >> 1)), 0);
      tma2d(sb + OFF_XB + (q & 3) * 8192, &maps.ft, fb, 64 * q, 64 * j);
    };
    if (elect_one()) {
      if (warp == 14) {
#pragma unroll
        for (int i = 0; i < B_FT; i++) mbar_init(bars + 8 * i, 1);
        asm volatile("fence.proxy.async.shared::cta;" ::: "memory");
        if (!helper) {
#pragma unroll 1
          for (int n = 0; n < 2; n++) {
            const uint32_t fb = bars + 8 * (B_FA + n);
            xf_load(2 * n); xf_load(2 * n + 1);
            mbar_expect_tx(fb, U);
            tma2d(sb + OFF_RING + n * U, &maps.g64, fb, f_full, 64 * n);
            tma2d(sb + OFF_RING + n * U + 8192, &maps.u64, fb, f_full, 64 * n);
          }
        }
      } else if (warp == 15) {
#pragma unroll
        for (int i = B_FT; i < NBAR; i++) mbar_init(bars + 8 * i, i < B_EA ? 1 : i < B_T ? 2 : 4);
#pragma unroll
        for (int i = 0; i < 8; i++) mbar_expect_tx(bars + 8 * (B_Z + i), U / 2);
        asm volatile("fence.mbarrier_init.release.cluster;" ::: "memory");
        asm volatile("fence.proxy.async.shared::cta;" ::: "memory");
      } else if (warp == 13) {
#pragma unroll
        for (int i = 1; i < 4; i++) asm volatile("prefetch.tensormap [%0];" ::"l"((const char*)&maps + i * 128) : "memory");
      }
    }
    __syncwarp();
    asm volatile("bar.arrive 0, 384;" ::: "memory");
    asm volatile("bar.arrive 4, 256;" ::: "memory");
    __syncwarp();
    asm volatile("barrier.cluster.arrive.relaxed.aligned;" ::: "memory");
    asm volatile("bar.sync 3, 128;" ::: "memory");
    if (warp == 15 && !helper) {
        mbar_wait(bars + 8 * B_FE, 0);
        const uint32_t tag = (ld_x1(&g_epoch[blockIdx.x * 8]) + 1) & 1;
        const int c = lane >> 4, jj = 16 * blockIdx.x + (lane & 15), jm = (2048 - jj) & 2047;
        const unsigned short* pr = (const unsigned short*)w_r + 256 * c;
        const unsigned short* pi = (const unsigned short*)w_i + 256 * c;
        const float wr = 0.25f * (bf_lo(__ldg(pr + jj * 257)) + bf_lo(__ldg(pr + jm * 257)));
        const float wi = 0.25f * (bf_lo(__ldg(pi + jj * 257)) - bf_lo(__ldg(pi + jm * 257)));
        st_u2(g_Wh + c * 2048 + jj, c ? pack_bf16(-wi, wr) : pack_bf16(wr, wi), tag);
        __syncwarp();
        hint_add_if(lane == 0, &g_cntW[0]);
      }
    if ((!helper || warp == 15) && elect_one()) {
      if (warp < 14) {
        const int p = warp - 12;
#pragma unroll 1
        for (int n = 2; n < 31; n++) {
          const bool table = n == 4 || n >= 29;
          const int q = n < 4 ? n : n - 1;
          const CUtensorMap* m = table ? &maps.e : n >= 25 ? &maps.g32 + p : &maps.g64 + p;
          const int c0 = table ? 0 : n >= 25 ? f_half : f_full + 64 * (q >> 3);
          const int c1 = table ? (2 * rb + ((n & 1) ^ 1)) * 128 + 64 * p : n >= 25 ? 128 * (n - 25) : 64 * (q & 7);
          const uint32_t fb = bars + 8 * (B_FA + (n & 3)), dst = sb + OFF_RING + (n & 3) * U + p * 8192;
          if (n < 4) mbar_wait(bars + 8 * (B_FE + n - 2), 0);
          else mbar_wait(bars + 8 * (B_EA + (n & 3)), ((n >> 2) & 1) ^ 1);
          tma2d(dst, m, fb, c0, c1);
          if (p == 0) mbar_expect_tx(fb, U);
        }
      } else if (warp == 15) {
        const unsigned ep1 = ld_x1(&g_epoch[blockIdx.x * 8]) + 1;
        flag_wait(&g_cntX[helper ? 0 : 32 * j], ep1 * 16u);
        PROF_EV(22);
        mbar_expect_tx(bars + 8 * B_HX, U);
        bulk_load(sb + OFF_XB, g_X + (size_t)(helper ? 128 : kg * 8 + tn) * 8192, U, bars + 8 * B_HX);
        if (!helper) {
          flag_wait(&g_cntT[32 * j], ep1 * 64u);
          PROF_EV(23);
          mbar_expect_tx(bars + 8 * B_TL, U);
          tma3d(sb + OFF_T, &maps.t, bars + 8 * B_TL, 64 * j, 0, 2 * rb);
#pragma unroll 1
          for (int i = 0; i < 3; i++) {
            mbar_wait(bars + 8 * (B_PZ + (i >> 1)), 0);
            flag_wait(&g_cntP[32 * (rb * 8 + j) + i], ep1 * 8u);
            if (i == 2) PROF_EV(26);
            mbar_expect_tx(bars + 8 * (B_HP + i), U);
            bulk_load(sb + i * U, g_part + (size_t)((rb * 8 + j) * 3 + i) * 1024, U, bars + 8 * (B_HP + i));
          }
          g_epoch[blockIdx.x * 8] = ep1;
        }
      } else {
#pragma unroll 1
        for (int q = 4; q < 8; q++) xf_load(q);
        mbar_wait(bars + 8 * (B_FE + 2), 0);
        mbar_expect_tx(bars + 8 * B_E0, U);
        tma2d(sb + OFF_XB, &maps.e, bars + 8 * B_E0, 0, 2 * rb * 128);
        tma2d(sb + OFF_XB + 8192, &maps.e, bars + 8 * B_E0, 0, 2 * rb * 128 + 64);
#pragma unroll 1
        for (int h2 = 0; h2 < 2; h2++) {
          const int s0 = 2 * rb + h2, sg = (s0 & ~6) | ((s0 & 2) << 1) | ((s0 & 4) >> 1);
          mbar_wait(bars + 8 * (B_XS + h2), 0);
#pragma unroll 1
          for (int c = 0; c < 2; c++) {
            asm volatile("cp.async.bulk.tensor.4d.global.shared::cta.bulk_group [%0, {%2, %3, %4, %5}], [%1];" ::"l"(&maps.xs),
                         "r"(sb + OFF_XB + h2 * 8192 + c * 4096), "r"(0), "r"(sg), "r"(0), "r"(16 * j + 8 * c) : "memory");
            if (j == 0)
              asm volatile("cp.async.bulk.global.shared::cta.bulk_group [%0], [%1], 256;" ::"l"(g_X + 128 * 8192 + c * 4096 + sg * 128),
                           "r"(sb + OFF_SP + h2 * 512 + c * 256) : "memory");
            if (SPACE && h2 + c < 2) __nanosleep(SPACE);
          }
        }
        bulk_done_signal(&g_cntX[32 * j]);
        PROF_EV(20);
#pragma unroll 1
        for (int t = 0; t < 8; t++) {
          const int i = t < 3 ? t + 1 : t < 6 ? t - 2 : 0;
          const int col = 64 * (2 * ((q4 + i) & 3) + ((t < 3 || t == 6) ? 1 - rank : rank));
          const uint32_t fb = bars + 8 * (B_FT + (t & 3)), dst = sb + (t & 3) * TB;
          mbar_wait(bars + 8 * (B_ET + (t == 2 ? 3 : t & 3)), t >> 2);
          mbar_expect_tx(fb, TB);
          tma2d(dst, &maps.d224, fb, col, 224 * j);
          if (t < 2) mbar_wait(bars + 8 * (B_ET + t + 1), 0);
          tma2d(dst + 28672, &maps.ft, fb, col, 64 * j);
        }
      }
    }
  }
}

typedef CUresult (*EncodeFn)(CUtensorMap*, CUtensorMapDataType, cuuint32_t, void*, const cuuint64_t*, const cuuint64_t*, const cuuint32_t*,
                             const cuuint32_t*, CUtensorMapInterleave, CUtensorMapSwizzle, CUtensorMapL2promotion, CUtensorMapFloatOOBfill);

static void encode(EncodeFn f, CUtensorMap* m, const void* base, int rank, const cuuint64_t* dims, const cuuint64_t* strides, const cuuint32_t* box,
                   CUtensorMapSwizzle sw) {
  cuuint32_t es[5] = {1, 1, 1, 1, 1};
  f(m, CU_TENSOR_MAP_DATA_TYPE_BFLOAT16, rank, (void*)base, dims, strides, box, es, CU_TENSOR_MAP_INTERLEAVE_NONE, sw,
    CU_TENSOR_MAP_L2_PROMOTION_L2_128B, CU_TENSOR_MAP_FLOAT_OOB_FILL_NONE);
}

extern "C" void kernel_launch(void* const* d_in, const int* in_sizes, int n_in, void* d_out, int out_size) {
  (void)in_sizes; (void)n_in; (void)out_size;
  const __nv_bfloat16* x = (const __nv_bfloat16*)d_in[0];
  const __nv_bfloat16* w_r = (const __nv_bfloat16*)d_in[1];
  const __nv_bfloat16* w_i = (const __nv_bfloat16*)d_in[2];
  const __nv_bfloat16* Wg = (const __nv_bfloat16*)d_in[4];
  const __nv_bfloat16* Wu = (const __nv_bfloat16*)d_in[5];
  const __nv_bfloat16* Wd = (const __nv_bfloat16*)d_in[6];
  const __nv_bfloat16* gw = (const __nv_bfloat16*)d_in[7];

  void* fp = nullptr; cudaDriverEntryPointQueryResult qr;
  cudaGetDriverEntryPoint("cuTensorMapEncodeTiled", &fp, cudaEnableDefault, &qr);
  EncodeFn enc = (EncodeFn)fp;
  void *pFT, *pET, *pX, *pT;
  cudaGetSymbolAddress(&pX, g_X); cudaGetSymbolAddress(&pT, g_T);
  cudaGetSymbolAddress(&pFT, g_FT); cudaGetSymbolAddress(&pET, g_ET);

  Maps mp;
  const CUtensorMapSwizzle S128 = CU_TENSOR_MAP_SWIZZLE_128B, S64 = CU_TENSOR_MAP_SWIZZLE_64B;
  { cuuint64_t d[3] = {512, 64, 32}, s[2] = {32768, 1024}; cuuint32_t b[3] = {64, 64, 2}; encode(enc, &mp.x, x, 3, d, s, b, S128); }
  { cuuint64_t d[2] = {512, 512}, s[1] = {1024}; cuuint32_t b[2] = {64, 64}; encode(enc, &mp.ft, pFT, 2, d, s, b, S128); }
  { cuuint64_t d[4] = {128, 32, 2, 129}, s[3] = {256, 8192, 16384}; cuuint32_t b[4] = {128, 1, 2, 8}; encode(enc, &mp.xs, pX, 4, d, s, b, CU_TENSOR_MAP_SWIZZLE_NONE); }
  { cuuint64_t d[3] = {512, 32, 64}, s[2] = {65536, 1024}; cuuint32_t b[3] = {32, 32, 2}; encode(enc, &mp.ts, pT, 3, d, s, b, S64); }
  { cuuint64_t d[3] = {512, 64, 32}, s[2] = {1024, 65536}; cuuint32_t b[3] = {64, 64, 2}; encode(enc, &mp.t, pT, 3, d, s, b, S128); }
  { cuuint64_t d[2] = {64, 4096}, s[1] = {128}; cuuint32_t b[2] = {64, 64}; encode(enc, &mp.e, pET, 2, d, s, b, S128); }
  { cuuint64_t d[2] = {1792, 512}, s[1] = {3584}; cuuint32_t b[2] = {64, 64}, b2[2] = {32, 128};
    encode(enc, &mp.g64, Wg, 2, d, s, b, S128); encode(enc, &mp.u64, Wu, 2, d, s, b, S128);
    encode(enc, &mp.g32, Wg, 2, d, s, b2, S64); encode(enc, &mp.u32, Wu, 2, d, s, b2, S64); }
  { cuuint64_t d[2] = {512, 1792}, s[1] = {1024}; cuuint32_t b[2] = {64, 224}; encode(enc, &mp.d224, Wd, 2, d, s, b, S128); }
  { cuuint64_t d[4] = {264, 32, 8, 8}, s[3] = {32896, 512, 4112}; cuuint32_t b[4] = {24, 32, 2, 1};
    encode(enc, &mp.wr, w_r, 4, d, s, b, CU_TENSOR_MAP_SWIZZLE_NONE); encode(enc, &mp.wi, w_i, 4, d, s, b, CU_TENSOR_MAP_SWIZZLE_NONE); }

  cudaFuncSetAttribute(fused_kernel, cudaFuncAttributeMaxDynamicSharedMemorySize, SMEM_BYTES);
  fused_kernel<<<NCTA, 512, SMEM_BYTES>>>(mp, w_r, w_i, gw, (__nv_bfloat16*)d_out);
}
```

```cpp
#include <cuda_runtime.h>
#include <cuda_bf16.h>
#include <cuda.h>
#include <stdint.h>

namespace tbl {
constexpr double PI = 3.14159265358979323846264338327950288;
constexpr double sin_s(double x) { double t = x, s = x; for (int n = 1; n < 12; n++) { t *= -x * x / ((2 * n) * (2 * n + 1)); s += t; } return s; }
constexpr double cos_s(double x) { double t = 1, s = 1; for (int n = 1; n < 12; n++) { t *= -x * x / ((2 * n - 1) * (2 * n)); s += t; } return s; }
constexpr double cos2048(int m) {
  m &= 2047; if (m > 1024) m = 2048 - m;
  bool neg = false; if (m > 512) { m = 1024 - m; neg = true; }
  double v = (m <= 256) ? cos_s(2 * PI * m / 2048) : sin_s(2 * PI * (512 - m) / 2048);
  return neg ? -v : v;
}
constexpr uint16_t to_bf16(double v) {
  if (v == 0) return 0;
  uint16_t s = 0; if (v < 0) { s = 0x8000; v = -v; }
  int e = 0; while (v >= 2) { v /= 2; e++; } while (v < 1) { v *= 2; e--; }
  double m = (v - 1) * 128; int mi = (int)m; double fr = m - mi;
  if (fr > 0.5 || (fr == 0.5 && (mi & 1))) mi++;
  if (mi == 128) { mi = 0; e++; }
  return (uint16_t)(s | ((e + 127) << 7) | mi);
}
struct CosT { uint16_t v[2048]; constexpr CosT() : v() { for (int i = 0; i < 2048; i++) v[i] = to_bf16(cos2048(i)); } };
struct alignas(1024) FT {
  uint16_t v[512 * 512];
  constexpr FT() : v() {
    CosT c;
    for (int r = 0; r < 512; r++) {
      int k = (r >> 4) * 8 + (r & 7), e = (r >> 3) & 1;
      int mul = 4 * k, add = e ? 512 : 0;
      if (k == 0 && e == 1) { mul = 1024; add = 0; }
      for (int d = 0; d < 512; d++) v[r * 512 + d] = c.v[(d * mul + add) & 2047];
    }
  }
};
struct alignas(1024) ET {
  uint16_t v[2048 * 128];
  constexpr ET() : v() {
    CosT c;
    for (int s = 0; s < 2048; s++)
      for (int j = 0; j < 64; j++) {
        const int o = (s & 31) * 8192 + (s >> 5) * 64 + j;
        v[o] = c.v[(s * j) & 2047]; v[o + 4096] = c.v[(s * j + 512) & 2047];
      }
  }
};
struct alignas(1024) DT {
  uint16_t v[64 * 64];
  constexpr DT() : v() {
    CosT c;
    for (int r = 0; r < 64; r++)
      for (int n = 0; n < 64; n++) {
        const int sg = r >> 1, s0 = (sg & ~6) | ((sg & 2) << 1) | ((sg & 4) >> 1), e = r & 1, f = n & 1;
        const int m = 64 * s0 * (n >> 1) + (e == f ? 0 : e ? -512 : 512);
        v[r * 64 + (((n >> 3) ^ (r & 7)) << 3) + (n & 7)] = c.v[m & 2047];
      }
  }
};
}

__device__ constexpr tbl::FT g_FT = tbl::FT();
__device__ constexpr tbl::ET g_ET = tbl::ET();
__device__ constexpr tbl::DT g_DT = tbl::DT();

__device__ __align__(1024) uint16_t g_X[129 * 8192];
__device__ __align__(1024) uint16_t g_T[32 * 64 * 512];
__device__ __align__(1024) uint2 g_Ts[32 * 64];
__device__ __align__(1024) uint4 g_part[128 * 3 * 1024];
__device__ __align__(16) float g_gate[16 * 128];
__device__ __align__(16) uint2 g_Wh[2 * 2048];
__device__ unsigned g_epoch[132 * 8];
__device__ unsigned g_cntX[8 * 32], g_cntT[8 * 32], g_cntP[128 * 32], g_cntW[32], g_cntH[32];
#define PROF_EV(i) do {} while (0)
#define PROF_CK(i) do {} while (0)

__device__ __forceinline__ uint32_t smem_u32(const void* p) { return (uint32_t)__cvta_generic_to_shared(p); }
__device__ __forceinline__ void mbar_init(uint32_t bar, uint32_t cnt) { asm volatile("mbarrier.init.shared::cta.b64 [%0], %1;" ::"r"(bar), "r"(cnt)); }
__device__ __forceinline__ void mbar_expect_tx(uint32_t bar, uint32_t bytes) { asm volatile("mbarrier.arrive.expect_tx.shared::cta.b64 _, [%0], %1;" ::"r"(bar), "r"(bytes) : "memory"); }
__device__ __forceinline__ void mbar_arrive(uint32_t bar) { asm volatile("mbarrier.arrive.shared::cta.b64 _, [%0];" ::"r"(bar) : "memory"); }
__device__ __forceinline__ bool elect_one() {
  uint32_t p;
  asm volatile("{\n.reg .pred p;\nelect.sync _|p, 0xffffffff;\nselp.u32 %0, 1, 0, p;\n}" : "=r"(p));
  return p;
}
__device__ __forceinline__ void mbar_arrive_if(bool p, uint32_t bar) {
  asm volatile("{\n.reg .pred p;\nsetp.ne.b32 p, %1, 0;\n@p mbarrier.arrive.shared::cta.b64 _, [%0];\n}" ::"r"(bar), "r"((int)p) : "memory");
}
__device__ __forceinline__ void hint_add_if(bool p, unsigned* a) {
  asm volatile("{\n.reg .pred p;\nsetp.ne.b32 p, %1, 0;\n@p red.relaxed.gpu.global.add.u32 [%0], 1;\n}" ::"l"(a), "r"((int)p) : "memory");
}
__device__ __forceinline__ bool mbar_try(uint32_t bar, uint32_t parity) {
  uint32_t ok;
  asm volatile("{\n.reg .pred p;\nmbarrier.test_wait.parity.shared::cta.b64 p, [%1], %2;\nselp.u32 %0, 1, 0, p;\n}" : "=r"(ok) : "r"(bar), "r"(parity) : "memory");
  return ok;
}
__device__ __forceinline__ void mbar_wait(uint32_t bar, uint32_t parity) {
  asm volatile(
      "{\n.reg .pred p;\n.reg .u32 n;\nmov.u32 n, 0;\n"
      "W_LOOP:\nmbarrier.try_wait.parity.shared::cta.b64 p, [%0], %1;\n@p bra W_DONE;\n"
      "add.u32 n, n, 1;\nsetp.lt.u32 p, n, 0x40000;\n@p bra W_LOOP;\ntrap;\nW_DONE:\n}" ::"r"(bar), "r"(parity) : "memory");
}
__device__ __forceinline__ void bulk_load(uint32_t dst, const void* src, uint32_t bytes, uint32_t bar) {
  asm volatile("cp.async.bulk.shared::cluster.global.mbarrier::complete_tx::bytes [%0], [%1], %2, [%3];" ::"r"(dst), "l"(src), "r"(bytes), "r"(bar) : "memory");
}
__device__ __forceinline__ void cp16(uint32_t dst, const void* src) { asm volatile("cp.async.cg.shared.global [%0], [%1], 16;" ::"r"(dst), "l"(src) : "memory"); }
__device__ __forceinline__ void spin_guard(uint32_t t0) { if ((uint32_t)clock() - t0 > (1u << 30)) __trap(); }
__device__ __forceinline__ float tagf(float v, uint32_t tag) { return __uint_as_float((__float_as_uint(v) & ~1u) | tag); }
__device__ __forceinline__ float untag(float v) { return __uint_as_float(__float_as_uint(v) & ~1u); }
__device__ __forceinline__ void st_x2(float2* p, float a, float b) { asm volatile("st.relaxed.gpu.global.v2.f32 [%0], {%1,%2};" ::"l"(p), "f"(a), "f"(b) : "memory"); }
__device__ __forceinline__ float2 ld_x2(const float2* p) { float2 v; asm volatile("ld.relaxed.gpu.global.v2.f32 {%0,%1}, [%2];" : "=f"(v.x), "=f"(v.y) : "l"(p) : "memory"); return v; }
__device__ __forceinline__ void st_u2(uint2* p, uint32_t a, uint32_t b) { asm volatile("st.relaxed.gpu.global.v2.u32 [%0], {%1,%2};" ::"l"(p), "r"(a), "r"(b) : "memory"); }
__device__ __forceinline__ void prefetch2d(const CUtensorMap* m, int c0, int c1) { asm volatile("cp.async.bulk.prefetch.tensor.2d.L2.global [%0, {%1, %2}];" ::"l"(m), "r"(c0), "r"(c1) : "memory"); }
__device__ __forceinline__ void prefetch1d(const void* p, uint32_t bytes) { asm volatile("cp.async.bulk.prefetch.L2.global [%0], %1;" ::"l"(p), "r"(bytes) : "memory"); }
__device__ __forceinline__ uint32_t ld_x1(const void* p) { uint32_t v; asm volatile("ld.relaxed.gpu.global.u32 %0, [%1];" : "=r"(v) : "l"(p) : "memory"); return v; }
__device__ __forceinline__ uint4 ld_x4(const void* p) { uint4 v; asm volatile("ld.relaxed.gpu.global.v4.u32 {%0,%1,%2,%3}, [%4];" : "=r"(v.x), "=r"(v.y), "=r"(v.z), "=r"(v.w) : "l"(p) : "memory"); return v; }
__device__ __forceinline__ void st_x4(void* p, uint32_t a, uint32_t b, uint32_t c, uint32_t d) { asm volatile("st.relaxed.gpu.global.v4.u32 [%0], {%1,%2,%3,%4};" ::"l"(p), "r"(a), "r"(b), "r"(c), "r"(d) : "memory"); }
__device__ __forceinline__ uint32_t mapa(uint32_t a, uint32_t cta) { uint32_t r; asm volatile("mapa.shared::cluster.u32 %0, %1, %2;" : "=r"(r) : "r"(a), "r"(cta)); return r; }
__device__ __forceinline__ void stsm4t(uint32_t a, uint32_t r0, uint32_t r1, uint32_t r2, uint32_t r3) {
  asm volatile("stmatrix.sync.aligned.m8n8.x4.trans.shared.b16 [%0], {%1,%2,%3,%4};" ::"r"(a), "r"(r0), "r"(r1), "r"(r2), "r"(r3) : "memory");
}
__device__ __forceinline__ void hint_add(unsigned* p) { asm volatile("red.relaxed.gpu.global.add.u32 [%0], 1;" ::"l"(p) : "memory"); }
__device__ __forceinline__ void hint_wait(const unsigned* p, unsigned target) {
  const uint32_t t0 = (uint32_t)clock();
  while ((int)(ld_x1(p) - target) < 0) spin_guard(t0);
}
__device__ __forceinline__ void bulk_done_signal(unsigned* p) {
  asm volatile("cp.async.bulk.commit_group;\ncp.async.bulk.wait_group 0;\nfence.proxy.async.global;" ::: "memory");
  hint_add(p);
}
__device__ __forceinline__ void flag_wait(const unsigned* p, unsigned target) {
  hint_wait(p, target);
  asm volatile("fence.proxy.async.global;" ::: "memory");
}
__device__ __forceinline__ void tma2d(uint32_t dst, const CUtensorMap* m, uint32_t bar, int c0, int c1) {
  asm volatile("cp.async.bulk.tensor.2d.shared::cluster.global.mbarrier::complete_tx::bytes [%0], [%1, {%3, %4}], [%2];" ::"r"(dst), "l"(m), "r"(bar), "r"(c0), "r"(c1) : "memory");
}
__device__ __forceinline__ void tma3d(uint32_t dst, const CUtensorMap* m, uint32_t bar, int c0, int c1, int c2) {
  asm volatile("cp.async.bulk.tensor.3d.shared::cluster.global.mbarrier::complete_tx::bytes [%0], [%1, {%3, %4, %5}], [%2];" ::"r"(dst), "l"(m), "r"(bar), "r"(c0), "r"(c1), "r"(c2) : "memory");
}
__device__ __forceinline__ void tma4d(uint32_t dst, const CUtensorMap* m, uint32_t bar, int c0, int c1, int c2, int c3) {
  asm volatile("cp.async.bulk.tensor.4d.shared::cluster.global.mbarrier::complete_tx::bytes [%0], [%1, {%3, %4, %5, %6}], [%2];" ::"r"(dst), "l"(m), "r"(bar), "r"(c0), "r"(c1), "r"(c2), "r"(c3) : "memory");
}
__device__ __forceinline__ void wg_fence() { asm volatile("wgmma.fence.sync.aligned;" ::: "memory"); }
__device__ __forceinline__ void wg_commit() { asm volatile("wgmma.commit_group.sync.aligned;" ::: "memory"); }
template <int N> __device__ __forceinline__ void wg_wait() { asm volatile("wgmma.wait_group.sync.aligned %0;" ::"n"(N) : "memory"); }
template <int O, int N, int NN> __device__ __forceinline__ void fence_regs(float (&d)[NN]) {
#pragma unroll
  for (int i = 0; i < N; i++) asm volatile("" : "+f"(d[O + i])::"memory");
}
__device__ __forceinline__ uint32_t pack_bf16(float lo, float hi) {
  uint32_t r; asm("cvt.rn.bf16x2.f32 %0, %1, %2;" : "=r"(r) : "f"(hi), "f"(lo)); return r;
}
__device__ __forceinline__ uint32_t pack_pin(float lo, float hi) {
  uint32_t r; asm volatile("cvt.rn.bf16x2.f32 %0, %1, %2;" : "=r"(r) : "f"(hi), "f"(lo) : "memory"); return r;
}
__device__ __forceinline__ float bf_lo(uint32_t u) { return __uint_as_float(u << 16); }
__device__ __forceinline__ float bf_hi(uint32_t u) { return __uint_as_float(u & 0xffff0000u); }

__device__ __forceinline__ uint64_t d128(uint32_t lo) { uint64_t d; asm("mov.b64 %0, {%1, 0x40000040};" : "=l"(d) : "r"(lo)); return d; }
__device__ __forceinline__ uint64_t d64(uint32_t lo) { uint64_t d; asm("mov.b64 %0, {%1, 0x80000020};" : "=l"(d) : "r"(lo)); return d; }
template<int O,int TB,int ACC,int NN> __device__ __forceinline__ void mma_ss64(float (&d)[NN], uint64_t da, uint64_t db, int sd = 0){
  if constexpr (ACC == 1) asm volatile("wgmma.mma_async.sync.aligned.m64n64k16.f32.bf16.bf16 {%0,%1,%2,%3,%4,%5,%6,%7,%8,%9,%10,%11,%12,%13,%14,%15,%16,%17,%18,%19,%20,%21,%22,%23,%24,%25,%26,%27,%28,%29,%30,%31}, %32, %33, 1, 1, 1, %35, %34;"
   : "+f"(d[O+0]), "+f"(d[O+1]), "+f"(d[O+2]), "+f"(d[O+3]), "+f"(d[O+4]), "+f"(d[O+5]), "+f"(d[O+6]), "+f"(d[O+7]), "+f"(d[O+8]), "+f"(d[O+9]), "+f"(d[O+10]), "+f"(d[O+11]), "+f"(d[O+12]), "+f"(d[O+13]), "+f"(d[O+14]), "+f"(d[O+15]), "+f"(d[O+16]), "+f"(d[O+17]), "+f"(d[O+18]), "+f"(d[O+19]), "+f"(d[O+20]), "+f"(d[O+21]), "+f"(d[O+22]), "+f"(d[O+23]), "+f"(d[O+24]), "+f"(d[O+25]), "+f"(d[O+26]), "+f"(d[O+27]), "+f"(d[O+28]), "+f"(d[O+29]), "+f"(d[O+30]), "+f"(d[O+31])
   : "l"(da), "l"(db), "n"(TB & 1), "n"(TB >> 1));
  else if constexpr (ACC == 0) asm volatile("wgmma.mma_async.sync.aligned.m64n64k16.f32.bf16.bf16 {%0,%1,%2,%3,%4,%5,%6,%7,%8,%9,%10,%11,%12,%13,%14,%15,%16,%17,%18,%19,%20,%21,%22,%23,%24,%25,%26,%27,%28,%29,%30,%31}, %32, %33, 0, 1, 1, %35, %34;"
   : "=f"(d[O+0]), "=f"(d[O+1]), "=f"(d[O+2]), "=f"(d[O+3]), "=f"(d[O+4]), "=f"(d[O+5]), "=f"(d[O+6]), "=f"(d[O+7]), "=f"(d[O+8]), "=f"(d[O+9]), "=f"(d[O+10]), "=f"(d[O+11]), "=f"(d[O+12]), "=f"(d[O+13]), "=f"(d[O+14]), "=f"(d[O+15]), "=f"(d[O+16]), "=f"(d[O+17]), "=f"(d[O+18]), "=f"(d[O+19]), "=f"(d[O+20]), "=f"(d[O+21]), "=f"(d[O+22]), "=f"(d[O+23]), "=f"(d[O+24]), "=f"(d[O+25]), "=f"(d[O+26]), "=f"(d[O+27]), "=f"(d[O+28]), "=f"(d[O+29]), "=f"(d[O+30]), "=f"(d[O+31])
   : "l"(da), "l"(db), "n"(TB & 1), "n"(TB >> 1));
  else asm volatile("{\n.reg .pred p;\nsetp.ne.b32 p, %36, 0;\nwgmma.mma_async.sync.aligned.m64n64k16.f32.bf16.bf16 {%0,%1,%2,%3,%4,%5,%6,%7,%8,%9,%10,%11,%12,%13,%14,%15,%16,%17,%18,%19,%20,%21,%22,%23,%24,%25,%26,%27,%28,%29,%30,%31}, %32, %33, p, 1, 1, %35, %34;\n}"
   : "+f"(d[O+0]), "+f"(d[O+1]), "+f"(d[O+2]), "+f"(d[O+3]), "+f"(d[O+4]), "+f"(d[O+5]), "+f"(d[O+6]), "+f"(d[O+7]), "+f"(d[O+8]), "+f"(d[O+9]), "+f"(d[O+10]), "+f"(d[O+11]), "+f"(d[O+12]), "+f"(d[O+13]), "+f"(d[O+14]), "+f"(d[O+15]), "+f"(d[O+16]), "+f"(d[O+17]), "+f"(d[O+18]), "+f"(d[O+19]), "+f"(d[O+20]), "+f"(d[O+21]), "+f"(d[O+22]), "+f"(d[O+23]), "+f"(d[O+24]), "+f"(d[O+25]), "+f"(d[O+26]), "+f"(d[O+27]), "+f"(d[O+28]), "+f"(d[O+29]), "+f"(d[O+30]), "+f"(d[O+31])
   : "l"(da), "l"(db), "n"(TB & 1), "n"(TB >> 1), "r"(sd));
}
template<int O,int TB,int ACC,int NN> __device__ __forceinline__ void mma_rs64(float (&d)[NN], uint32_t a0, uint32_t a1, uint32_t a2, uint32_t a3, uint64_t db, int sd = 0){
  if constexpr (ACC == 1) asm volatile("wgmma.mma_async.sync.aligned.m64n64k16.f32.bf16.bf16 {%0,%1,%2,%3,%4,%5,%6,%7,%8,%9,%10,%11,%12,%13,%14,%15,%16,%17,%18,%19,%20,%21,%22,%23,%24,%25,%26,%27,%28,%29,%30,%31}, {%32,%33,%34,%35}, %36, 1, 1, 1, %37;"
   : "+f"(d[O+0]), "+f"(d[O+1]), "+f"(d[O+2]), "+f"(d[O+3]), "+f"(d[O+4]), "+f"(d[O+5]), "+f"(d[O+6]), "+f"(d[O+7]), "+f"(d[O+8]), "+f"(d[O+9]), "+f"(d[O+10]), "+f"(d[O+11]), "+f"(d[O+12]), "+f"(d[O+13]), "+f"(d[O+14]), "+f"(d[O+15]), "+f"(d[O+16]), "+f"(d[O+17]), "+f"(d[O+18]), "+f"(d[O+19]), "+f"(d[O+20]), "+f"(d[O+21]), "+f"(d[O+22]), "+f"(d[O+23]), "+f"(d[O+24]), "+f"(d[O+25]), "+f"(d[O+26]), "+f"(d[O+27]), "+f"(d[O+28]), "+f"(d[O+29]), "+f"(d[O+30]), "+f"(d[O+31])
   : "r"(a0), "r"(a1), "r"(a2), "r"(a3), "l"(db), "n"(TB));
  else if constexpr (ACC == 0) asm volatile("wgmma.mma_async.sync.aligned.m64n64k16.f32.bf16.bf16 {%0,%1,%2,%3,%4,%5,%6,%7,%8,%9,%10,%11,%12,%13,%14,%15,%16,%17,%18,%19,%20,%21,%22,%23,%24,%25,%26,%27,%28,%29,%30,%31}, {%32,%33,%34,%35}, %36, 0, 1, 1, %37;"
   : "=f"(d[O+0]), "=f"(d[O+1]), "=f"(d[O+2]), "=f"(d[O+3]), "=f"(d[O+4]), "=f"(d[O+5]), "=f"(d[O+6]), "=f"(d[O+7]), "=f"(d[O+8]), "=f"(d[O+9]), "=f"(d[O+10]), "=f"(d[O+11]), "=f"(d[O+12]), "=f"(d[O+13]), "=f"(d[O+14]), "=f"(d[O+15]), "=f"(d[O+16]), "=f"(d[O+17]), "=f"(d[O+18]), "=f"(d[O+19]), "=f"(d[O+20]), "=f"(d[O+21]), "=f"(d[O+22]), "=f"(d[O+23]), "=f"(d[O+24]), "=f"(d[O+25]), "=f"(d[O+26]), "=f"(d[O+27]), "=f"(d[O+28]), "=f"(d[O+29]), "=f"(d[O+30]), "=f"(d[O+31])
   : "r"(a0), "r"(a1), "r"(a2), "r"(a3), "l"(db), "n"(TB));
  else asm volatile("{\n.reg .pred p;\nsetp.ne.b32 p, %38, 0;\nwgmma.mma_async.sync.aligned.m64n64k16.f32.bf16.bf16 {%0,%1,%2,%3,%4,%5,%6,%7,%8,%9,%10,%11,%12,%13,%14,%15,%16,%17,%18,%19,%20,%21,%22,%23,%24,%25,%26,%27,%28,%29,%30,%31}, {%32,%33,%34,%35}, %36, p, 1, 1, %37;\n}"
   : "+f"(d[O+0]), "+f"(d[O+1]), "+f"(d[O+2]), "+f"(d[O+3]), "+f"(d[O+4]), "+f"(d[O+5]), "+f"(d[O+6]), "+f"(d[O+7]), "+f"(d[O+8]), "+f"(d[O+9]), "+f"(d[O+10]), "+f"(d[O+11]), "+f"(d[O+12]), "+f"(d[O+13]), "+f"(d[O+14]), "+f"(d[O+15]), "+f"(d[O+16]), "+f"(d[O+17]), "+f"(d[O+18]), "+f"(d[O+19]), "+f"(d[O+20]), "+f"(d[O+21]), "+f"(d[O+22]), "+f"(d[O+23]), "+f"(d[O+24]), "+f"(d[O+25]), "+f"(d[O+26]), "+f"(d[O+27]), "+f"(d[O+28]), "+f"(d[O+29]), "+f"(d[O+30]), "+f"(d[O+31])
   : "r"(a0), "r"(a1), "r"(a2), "r"(a3), "l"(db), "n"(TB), "r"(sd));
}
template<int O,int TB,int ACC,int NN> __device__ __forceinline__ void mma_ss128(float (&d)[NN], uint64_t da, uint64_t db, int sd = 0){
  if constexpr (ACC == 1) asm volatile("wgmma.mma_async.sync.aligned.m64n128k16.f32.bf16.bf16 {%0,%1,%2,%3,%4,%5,%6,%7,%8,%9,%10,%11,%12,%13,%14,%15,%16,%17,%18,%19,%20,%21,%22,%23,%24,%25,%26,%27,%28,%29,%30,%31,%32,%33,%34,%35,%36,%37,%38,%39,%40,%41,%42,%43,%44,%45,%46,%47,%48,%49,%50,%51,%52,%53,%54,%55,%56,%57,%58,%59,%60,%61,%62,%63}, %64, %65, 1, 1, 1, %67, %66;"
   : "+f"(d[O+0]), "+f"(d[O+1]), "+f"(d[O+2]), "+f"(d[O+3]), "+f"(d[O+4]), "+f"(d[O+5]), "+f"(d[O+6]), "+f"(d[O+7]), "+f"(d[O+8]), "+f"(d[O+9]), "+f"(d[O+10]), "+f"(d[O+11]), "+f"(d[O+12]), "+f"(d[O+13]), "+f"(d[O+14]), "+f"(d[O+15]), "+f"(d[O+16]), "+f"(d[O+17]), "+f"(d[O+18]), "+f"(d[O+19]), "+f"(d[O+20]), "+f"(d[O+21]), "+f"(d[O+22]), "+f"(d[O+23]), "+f"(d[O+24]), "+f"(d[O+25]), "+f"(d[O+26]), "+f"(d[O+27]), "+f"(d[O+28]), "+f"(d[O+29]), "+f"(d[O+30]), "+f"(d[O+31]), "+f"(d[O+32]), "+f"(d[O+33]), "+f"(d[O+34]), "+f"(d[O+35]), "+f"(d[O+36]), "+f"(d[O+37]), "+f"(d[O+38]), "+f"(d[O+39]), "+f"(d[O+40]), "+f"(d[O+41]), "+f"(d[O+42]), "+f"(d[O+43]), "+f"(d[O+44]), "+f"(d[O+45]), "+f"(d[O+46]), "+f"(d[O+47]), "+f"(d[O+48]), "+f"(d[O+49]), "+f"(d[O+50]), "+f"(d[O+51]), "+f"(d[O+52]), "+f"(d[O+53]), "+f"(d[O+54]), "+f"(d[O+55]), "+f"(d[O+56]), "+f"(d[O+57]), "+f"(d[O+58]), "+f"(d[O+59]), "+f"(d[O+60]), "+f"(d[O+61]), "+f"(d[O+62]), "+f"(d[O+63])
   : "l"(da), "l"(db), "n"(TB & 1), "n"(TB >> 1));
  else if constexpr (ACC == 0) asm volatile("wgmma.mma_async.sync.aligned.m64n128k16.f32.bf16.bf16 {%0,%1,%2,%3,%4,%5,%6,%7,%8,%9,%10,%11,%12,%13,%14,%15,%16,%17,%18,%19,%20,%21,%22,%23,%24,%25,%26,%27,%28,%29,%30,%31,%32,%33,%34,%35,%36,%37,%38,%39,%40,%41,%42,%43,%44,%45,%46,%47,%48,%49,%50,%51,%52,%53,%54,%55,%56,%57,%58,%59,%60,%61,%62,%63}, %64, %65, 0, 1, 1, %67, %66;"
   : "=f"(d[O+0]), "=f"(d[O+1]), "=f"(d[O+2]), "=f"(d[O+3]), "=f"(d[O+4]), "=f"(d[O+5]), "=f"(d[O+6]), "=f"(d[O+7]), "=f"(d[O+8]), "=f"(d[O+9]), "=f"(d[O+10]), "=f"(d[O+11]), "=f"(d[O+12]), "=f"(d[O+13]), "=f"(d[O+14]), "=f"(d[O+15]), "=f"(d[O+16]), "=f"(d[O+17]), "=f"(d[O+18]), "=f"(d[O+19]), "=f"(d[O+20]), "=f"(d[O+21]), "=f"(d[O+22]), "=f"(d[O+23]), "=f"(d[O+24]), "=f"(d[O+25]), "=f"(d[O+26]), "=f"(d[O+27]), "=f"(d[O+28]), "=f"(d[O+29]), "=f"(d[O+30]), "=f"(d[O+31]), "=f"(d[O+32]), "=f"(d[O+33]), "=f"(d[O+34]), "=f"(d[O+35]), "=f"(d[O+36]), "=f"(d[O+37]), "=f"(d[O+38]), "=f"(d[O+39]), "=f"(d[O+40]), "=f"(d[O+41]), "=f"(d[O+42]), "=f"(d[O+43]), "=f"(d[O+44]), "=f"(d[O+45]), "=f"(d[O+46]), "=f"(d[O+47]), "=f"(d[O+48]), "=f"(d[O+49]), "=f"(d[O+50]), "=f"(d[O+51]), "=f"(d[O+52]), "=f"(d[O+53]), "=f"(d[O+54]), "=f"(d[O+55]), "=f"(d[O+56]), "=f"(d[O+57]), "=f"(d[O+58]), "=f"(d[O+59]), "=f"(d[O+60]), "=f"(d[O+61]), "=f"(d[O+62]), "=f"(d[O+63])
   : "l"(da), "l"(db), "n"(TB & 1), "n"(TB >> 1));
  else asm volatile("{\n.reg .pred p;\nsetp.ne.b32 p, %68, 0;\nwgmma.mma_async.sync.aligned.m64n128k16.f32.bf16.bf16 {%0,%1,%2,%3,%4,%5,%6,%7,%8,%9,%10,%11,%12,%13,%14,%15,%16,%17,%18,%19,%20,%21,%22,%23,%24,%25,%26,%27,%28,%29,%30,%31,%32,%33,%34,%35,%36,%37,%38,%39,%40,%41,%42,%43,%44,%45,%46,%47,%48,%49,%50,%51,%52,%53,%54,%55,%56,%57,%58,%59,%60,%61,%62,%63}, %64, %65, p, 1, 1, %67, %66;\n}"
   : "+f"(d[O+0]), "+f"(d[O+1]), "+f"(d[O+2]), "+f"(d[O+3]), "+f"(d[O+4]), "+f"(d[O+5]), "+f"(d[O+6]), "+f"(d[O+7]), "+f"(d[O+8]), "+f"(d[O+9]), "+f"(d[O+10]), "+f"(d[O+11]), "+f"(d[O+12]), "+f"(d[O+13]), "+f"(d[O+14]), "+f"(d[O+15]), "+f"(d[O+16]), "+f"(d[O+17]), "+f"(d[O+18]), "+f"(d[O+19]), "+f"(d[O+20]), "+f"(d[O+21]), "+f"(d[O+22]), "+f"(d[O+23]), "+f"(d[O+24]), "+f"(d[O+25]), "+f"(d[O+26]), "+f"(d[O+27]), "+f"(d[O+28]), "+f"(d[O+29]), "+f"(d[O+30]), "+f"(d[O+31]), "+f"(d[O+32]), "+f"(d[O+33]), "+f"(d[O+34]), "+f"(d[O+35]), "+f"(d[O+36]), "+f"(d[O+37]), "+f"(d[O+38]), "+f"(d[O+39]), "+f"(d[O+40]), "+f"(d[O+41]), "+f"(d[O+42]), "+f"(d[O+43]), "+f"(d[O+44]), "+f"(d[O+45]), "+f"(d[O+46]), "+f"(d[O+47]), "+f"(d[O+48]), "+f"(d[O+49]), "+f"(d[O+50]), "+f"(d[O+51]), "+f"(d[O+52]), "+f"(d[O+53]), "+f"(d[O+54]), "+f"(d[O+55]), "+f"(d[O+56]), "+f"(d[O+57]), "+f"(d[O+58]), "+f"(d[O+59]), "+f"(d[O+60]), "+f"(d[O+61]), "+f"(d[O+62]), "+f"(d[O+63])
   : "l"(da), "l"(db), "n"(TB & 1), "n"(TB >> 1), "r"(sd));
}
template<int O,int TB,int ACC,int NN> __device__ __forceinline__ void mma_rs128(float (&d)[NN], uint32_t a0, uint32_t a1, uint32_t a2, uint32_t a3, uint64_t db, int sd = 0){
  if constexpr (ACC == 1) asm volatile("wgmma.mma_async.sync.aligned.m64n128k16.f32.bf16.bf16 {%0,%1,%2,%3,%4,%5,%6,%7,%8,%9,%10,%11,%12,%13,%14,%15,%16,%17,%18,%19,%20,%21,%22,%23,%24,%25,%26,%27,%28,%29,%30,%31,%32,%33,%34,%35,%36,%37,%38,%39,%40,%41,%42,%43,%44,%45,%46,%47,%48,%49,%50,%51,%52,%53,%54,%55,%56,%57,%58,%59,%60,%61,%62,%63}, {%64,%65,%66,%67}, %68, 1, 1, 1, %69;"
   : "+f"(d[O+0]), "+f"(d[O+1]), "+f"(d[O+2]), "+f"(d[O+3]), "+f"(d[O+4]), "+f"(d[O+5]), "+f"(d[O+6]), "+f"(d[O+7]), "+f"(d[O+8]), "+f"(d[O+9]), "+f"(d[O+10]), "+f"(d[O+11]), "+f"(d[O+12]), "+f"(d[O+13]), "+f"(d[O+14]), "+f"(d[O+15]), "+f"(d[O+16]), "+f"(d[O+17]), "+f"(d[O+18]), "+f"(d[O+19]), "+f"(d[O+20]), "+f"(d[O+21]), "+f"(d[O+22]), "+f"(d[O+23]), "+f"(d[O+24]), "+f"(d[O+25]), "+f"(d[O+26]), "+f"(d[O+27]), "+f"(d[O+28]), "+f"(d[O+29]), "+f"(d[O+30]), "+f"(d[O+31]), "+f"(d[O+32]), "+f"(d[O+33]), "+f"(d[O+34]), "+f"(d[O+35]), "+f"(d[O+36]), "+f"(d[O+37]), "+f"(d[O+38]), "+f"(d[O+39]), "+f"(d[O+40]), "+f"(d[O+41]), "+f"(d[O+42]), "+f"(d[O+43]), "+f"(d[O+44]), "+f"(d[O+45]), "+f"(d[O+46]), "+f"(d[O+47]), "+f"(d[O+48]), "+f"(d[O+49]), "+f"(d[O+50]), "+f"(d[O+51]), "+f"(d[O+52]), "+f"(d[O+53]), "+f"(d[O+54]), "+f"(d[O+55]), "+f"(d[O+56]), "+f"(d[O+57]), "+f"(d[O+58]), "+f"(d[O+59]), "+f"(d[O+60]), "+f"(d[O+61]), "+f"(d[O+62]), "+f"(d[O+63])
   : "r"(a0), "r"(a1), "r"(a2), "r"(a3), "l"(db), "n"(TB));
  else if constexpr (ACC == 0) asm volatile("wgmma.mma_async.sync.aligned.m64n128k16.f32.bf16.bf16 {%0,%1,%2,%3,%4,%5,%6,%7,%8,%9,%10,%11,%12,%13,%14,%15,%16,%17,%18,%19,%20,%21,%22,%23,%24,%25,%26,%27,%28,%29,%30,%31,%32,%33,%34,%35,%36,%37,%38,%39,%40,%41,%42,%43,%44,%45,%46,%47,%48,%49,%50,%51,%52,%53,%54,%55,%56,%57,%58,%59,%60,%61,%62,%63}, {%64,%65,%66,%67}, %68, 0, 1, 1, %69;"
   : "=f"(d[O+0]), "=f"(d[O+1]), "=f"(d[O+2]), "=f"(d[O+3]), "=f"(d[O+4]), "=f"(d[O+5]), "=f"(d[O+6]), "=f"(d[O+7]), "=f"(d[O+8]), "=f"(d[O+9]), "=f"(d[O+10]), "=f"(d[O+11]), "=f"(d[O+12]), "=f"(d[O+13]), "=f"(d[O+14]), "=f"(d[O+15]), "=f"(d[O+16]), "=f"(d[O+17]), "=f"(d[O+18]), "=f"(d[O+19]), "=f"(d[O+20]), "=f"(d[O+21]), "=f"(d[O+22]), "=f"(d[O+23]), "=f"(d[O+24]), "=f"(d[O+25]), "=f"(d[O+26]), "=f"(d[O+27]), "=f"(d[O+28]), "=f"(d[O+29]), "=f"(d[O+30]), "=f"(d[O+31]), "=f"(d[O+32]), "=f"(d[O+33]), "=f"(d[O+34]), "=f"(d[O+35]), "=f"(d[O+36]), "=f"(d[O+37]), "=f"(d[O+38]), "=f"(d[O+39]), "=f"(d[O+40]), "=f"(d[O+41]), "=f"(d[O+42]), "=f"(d[O+43]), "=f"(d[O+44]), "=f"(d[O+45]), "=f"(d[O+46]), "=f"(d[O+47]), "=f"(d[O+48]), "=f"(d[O+49]), "=f"(d[O+50]), "=f"(d[O+51]), "=f"(d[O+52]), "=f"(d[O+53]), "=f"(d[O+54]), "=f"(d[O+55]), "=f"(d[O+56]), "=f"(d[O+57]), "=f"(d[O+58]), "=f"(d[O+59]), "=f"(d[O+60]), "=f"(d[O+61]), "=f"(d[O+62]), "=f"(d[O+63])
   : "r"(a0), "r"(a1), "r"(a2), "r"(a3), "l"(db), "n"(TB));
  else asm volatile("{\n.reg .pred p;\nsetp.ne.b32 p, %70, 0;\nwgmma.mma_async.sync.aligned.m64n128k16.f32.bf16.bf16 {%0,%1,%2,%3,%4,%5,%6,%7,%8,%9,%10,%11,%12,%13,%14,%15,%16,%17,%18,%19,%20,%21,%22,%23,%24,%25,%26,%27,%28,%29,%30,%31,%32,%33,%34,%35,%36,%37,%38,%39,%40,%41,%42,%43,%44,%45,%46,%47,%48,%49,%50,%51,%52,%53,%54,%55,%56,%57,%58,%59,%60,%61,%62,%63}, {%64,%65,%66,%67}, %68, p, 1, 1, %69;\n}"
   : "+f"(d[O+0]), "+f"(d[O+1]), "+f"(d[O+2]), "+f"(d[O+3]), "+f"(d[O+4]), "+f"(d[O+5]), "+f"(d[O+6]), "+f"(d[O+7]), "+f"(d[O+8]), "+f"(d[O+9]), "+f"(d[O+10]), "+f"(d[O+11]), "+f"(d[O+12]), "+f"(d[O+13]), "+f"(d[O+14]), "+f"(d[O+15]), "+f"(d[O+16]), "+f"(d[O+17]), "+f"(d[O+18]), "+f"(d[O+19]), "+f"(d[O+20]), "+f"(d[O+21]), "+f"(d[O+22]), "+f"(d[O+23]), "+f"(d[O+24]), "+f"(d[O+25]), "+f"(d[O+26]), "+f"(d[O+27]), "+f"(d[O+28]), "+f"(d[O+29]), "+f"(d[O+30]), "+f"(d[O+31]), "+f"(d[O+32]), "+f"(d[O+33]), "+f"(d[O+34]), "+f"(d[O+35]), "+f"(d[O+36]), "+f"(d[O+37]), "+f"(d[O+38]), "+f"(d[O+39]), "+f"(d[O+40]), "+f"(d[O+41]), "+f"(d[O+42]), "+f"(d[O+43]), "+f"(d[O+44]), "+f"(d[O+45]), "+f"(d[O+46]), "+f"(d[O+47]), "+f"(d[O+48]), "+f"(d[O+49]), "+f"(d[O+50]), "+f"(d[O+51]), "+f"(d[O+52]), "+f"(d[O+53]), "+f"(d[O+54]), "+f"(d[O+55]), "+f"(d[O+56]), "+f"(d[O+57]), "+f"(d[O+58]), "+f"(d[O+59]), "+f"(d[O+60]), "+f"(d[O+61]), "+f"(d[O+62]), "+f"(d[O+63])
   : "r"(a0), "r"(a1), "r"(a2), "r"(a3), "l"(db), "n"(TB), "r"(sd));
}

#define NEARLY 0
#define XAHEAD 3
#define HEADN 6
#define WBATCH 1
#define NOLDS 2
#define NOSEND 0
#define MSPLIT 3
#define SPACE 0
#define WPF 1
#define WAFTER 7
#define WPACE 0
#define GATE_AT 4
#define TPACE 40
#define PFMODE 0
#define MAPMODE 0
template <int V> struct IC { static constexpr int value = V; };
struct Maps { CUtensorMap x, ft, g64, u64, e, wr, wi, xs, ts, t, g32, u32, d224, o; };

constexpr int NCTA = 130;
constexpr int U = 16384;
constexpr int TB = 36864;
constexpr int OFF_RING = 8 * U, OFF_Z = 9 * U, OFF_XB = 12 * U, OFF_T = 13 * U, OFF_D = OFF_T;
constexpr int OFF_BAR = 14 * U, OFF_SP = OFF_BAR + 512, OFF_G = OFF_SP + 1024 + 128;
constexpr int SMEM_BYTES = OFF_G + 512;
constexpr int B_FX = 0, B_FA = 8, B_FT = 12, B_Z = 16, B_W = 24, B_HX = 25, B_TL = 26, B_HP = 27, B_WR = 30, B_E0 = 34;
constexpr int B_EA = 35, B_ET = 39, B_PZ = 43, B_RDY = 45, B_FE = 46;
constexpr int B_T = 50, B_XS = 51, B_G = 53, NBAR = 54;
__host__ __device__ constexpr int rslot(int n) { return n & 3; }
__host__ __device__ constexpr int rpar(int n) { return (n >> 2) & 1; }

__global__ void __cluster_dims__(2, 1, 1) __launch_bounds__(512, 1)
fused_kernel(const __grid_constant__ Maps maps, const __nv_bfloat16* __restrict__ w_r,
             const __nv_bfloat16* __restrict__ w_i, const __nv_bfloat16* __restrict__ gate_w) {
  extern __shared__ __align__(1024) uint8_t smem[];
  const uint32_t sb = smem_u32(smem);
  const uint32_t bars = sb + OFF_BAR;
  const int tid = threadIdx.x, lane = tid & 31;
  const int warp = __shfl_sync(0xffffffffu, tid >> 5, 0);
  const bool helper = blockIdx.x >= 128;
  const int cl = (blockIdx.x >> 1) & 63, rank = blockIdx.x & 1;
  const int q4 = cl & 3, rb = cl >> 2;
  const int j = 2 * q4 + rank;
  const int f_full = 448 * q4 + (rank ? 256 : 0);
  const int f_half = 448 * q4 + (rank ? 224 : 192);
  const int kg = 2 * j + (rb >> 3), tn = rb & 7;

  if (tid == 64) { PROF_EV(0); PROF_CK(40); }
  if (warp < 8) {
    asm volatile("barrier.cluster.arrive.relaxed.aligned;" ::: "memory");
    asm volatile("setmaxnreg.inc.sync.aligned.u32 192;");
    if (!helper) {
      const int wg = warp >> 2, w = warp & 3, g = lane >> 2;
      const bool elect = (tid & 127) == 0;
      float cX[32], cA[64], cB[64], cC[64], ci[64], ct[64];
      const int zero = blockIdx.x >> 16;
      uint32_t h[56], yf[16];
      const uint32_t d0 = (sb & 0x3FFFF) >> 4;
      const uint32_t dK = d0 | (1u << 16), dN = d0 | (512u << 16);
      const uint32_t dX = dK + wg * 512;
      constexpr uint32_t RING = OFF_RING >> 4;
      auto waitA = [&](int n) { mbar_wait(bars + 8 * (B_FA + rslot(n)), rpar(n)); };
      auto freeA = [&](int n) { mbar_arrive_if(elect, bars + 8 * (B_EA + rslot(n))); };
      auto nop = [] {};

      asm volatile("bar.sync 0, 384;" ::: "memory");
#pragma unroll 1
      for (int i = 0; i < 4; i++) {
        const uint64_t dx = d128(dX + i * 2048), df = d128(dK + (OFF_XB >> 4) + (i & 1) * 1024);
        mbar_wait(bars + 8 * (B_FX + 2 * i), 0);
        wg_fence();
        mma_ss64<0, 0, 2>(cX, df, dx, i);
        mma_ss64<0, 0, 1>(cX, df + 2, dx + 2);
        wg_commit(); wg_wait<1>();
        mbar_arrive_if(elect && i, bars + 8 * (B_EA + rslot(i - 1)));
        mma_ss64<0, 0, 1>(cX, df + 4, dx + 4);
        mma_ss64<0, 0, 1>(cX, df + 6, dx + 6);
        if (i == 0 && tid == 0) PROF_EV(1);
        mbar_wait(bars + 8 * (B_FX + 2 * i + 1), 0);
        wg_fence();
#pragma unroll
        for (int k = 0; k < 4; k++) mma_ss64<0, 0, 1>(cX, df + (512 + k * 2), dx + (1024 + k * 2));
        wg_commit();
        waitA(i);
        wg_fence();
        const uint64_t da = d128(dX + i * 1024), db = d128(dN + RING + i * 1024);
        mma_ss128<0, 1, 2>(cA, da, db, i);
        wg_commit(); wg_wait<1>();
        mbar_arrive_if(elect, bars + 8 * (B_FE + i));
#pragma unroll
        for (int k = 1; k < 4; k++) mma_ss128<0, 1, 1>(cA, da + k * 2, db + k * 128);
        wg_commit();
      }
      fence_regs<0, 32>(cX);
#pragma unroll
      for (int e = 0; e < 16; e++) yf[e] = pack_pin(cX[2 * e], cX[2 * e + 1]);
      if (tid == 0) PROF_EV(2);
      {
        waitA(4); mbar_wait(bars + 8 * B_E0, 0);
        const uint64_t de = d128(dN + (wg ? RING : OFF_XB >> 4));
        wg_fence();
        mma_rs128<0, 1, 0>(cB, yf[0], yf[1], yf[2], yf[3], de);
        wg_commit();
        wg_wait<1>();
        freeA(3);
#pragma unroll
        for (int k = 1; k < 4; k++) mma_rs128<0, 1, 1>(cB, yf[4 * k], yf[4 * k + 1], yf[4 * k + 2], yf[4 * k + 3], de + k * 128);
        wg_commit();
      }
      bool rel = false;
      auto acquire = [&](int n) {
        rel = elect;
        if (!mbar_try(bars + 8 * (B_FA + rslot(n)), rpar(n))) { wg_wait<0>(); freeA(n - 1); rel = false; waitA(n); }
      };
      auto freeP = [&](int n) { mbar_arrive_if(rel, bars + 8 * (B_EA + rslot(n - 1))); };
      auto ffn_step = [&](auto first, auto split, float (&acc)[64], int n, int kb, auto done, auto work) {
        constexpr int SPLIT = decltype(split)::value;
        acquire(n);
        wg_fence();
        const uint64_t dx = d128(dX + kb * 1024), db = d128(dN + RING + rslot(n) * 1024);
        mma_ss128<0, 1, decltype(first)::value>(acc, dx, db, kb);
#pragma unroll
        for (int k = 1; k < SPLIT; k++) mma_ss128<0, 1, 1>(acc, dx + k * 2, db + k * 128);
        wg_commit();
        work();
        wg_wait<1>();
        freeP(n);
        done();
        if (SPLIT < 4) {
          wg_fence();
#pragma unroll
          for (int k = SPLIT; k < 4; k++) mma_ss128<0, 1, 1>(acc, dx + k * 2, db + k * 128);
          wg_commit();
        }
      };
      {
        const int s0 = 2 * rb + wg, kr = 2 * ((s0 & 1) | ((s0 & 4) >> 1));
        const int m = lane >> 3, r = lane & 7;
        const uint32_t a0 = sb + OFF_XB + wg * 8192 + (((w >> 1) * 8 + (m >> 1)) * 2 + (w & 1)) * 256 + (m & 1) * 128 + ((r ^ (kr + (m & 1))) << 4);
        ffn_step(IC<1>(), IC<4>(), cA, 5, 4, [&] { fence_regs<0, 64>(cB); }, nop);
        asm volatile("bar.sync 5, 256;" ::: "memory");
#pragma unroll
        for (int i = 0; i < 4; i++)
          stsm4t(a0 + i * 1024, pack_bf16(cB[8 * i] - cB[34 + 8 * i], cB[8 * i + 1] - cB[35 + 8 * i]),
                 pack_bf16(cB[32 + 8 * i] + cB[8 * i + 2], cB[33 + 8 * i] + cB[8 * i + 3]),
                 pack_bf16(cB[8 * i + 4] - cB[38 + 8 * i], cB[8 * i + 5] - cB[39 + 8 * i]),
                 pack_bf16(cB[36 + 8 * i] + cB[8 * i + 6], cB[37 + 8 * i] + cB[8 * i + 7]));
        if (j == 0 && w == 0) {
          const uint32_t a1 = r ? sb + OFF_SP + 1024 : sb + OFF_SP + wg * 512 + (m & 1) * 256 + (m >> 1) * 128;
#pragma unroll
          for (int n = 0; n < 8; n++)
            asm volatile("stmatrix.sync.aligned.m8n8.x4.shared.b16 [%0], {%1,%2,%3,%4};" ::"r"(a1 + ((n ^ (kr + (m >> 1))) << 4)),
                         "r"(pack_bf16(cB[4 * n], cB[4 * n + 1])), "r"(pack_bf16(cB[4 * n + 2], cB[4 * n + 3])),
                         "r"(pack_bf16(cB[32 + 4 * n], cB[33 + 4 * n])), "r"(pack_bf16(cB[34 + 4 * n], cB[35 + 4 * n])) : "memory");
        }
        ffn_step(IC<1>(), IC<2>(), cA, 6, 5, nop, [&] {
          asm volatile("fence.proxy.async.shared::cta;" ::: "memory");
          __syncwarp();
          mbar_arrive_if(lane == 0, bars + 8 * (B_XS + wg));
          if (tid == 0) PROF_EV(3);
        });
      }
#pragma unroll 1
      for (int kb = 6; kb < 8; kb++) ffn_step(IC<1>(), IC<1>(), cA, 1 + kb, kb, nop, nop);
      float g0 = 0.f, g1 = 0.f;
      uint32_t tag = 0;
      auto glu = [&](auto& acc, int half, int ho, int i0, int i1) {
#pragma unroll
        for (int i = i0; i < i1; i++) {
          const float o = 1.0f - ((i & 1) ? g1 : g0);
          asm volatile("" : "+f"(acc[2 * i]), "+f"(acc[2 * i + 1]), "+f"(acc[half + 2 * i]), "+f"(acc[half + 1 + 2 * i])::"memory");
          h[ho + i] = pack_pin(fmaxf(acc[2 * i], 0.f) * acc[half + 2 * i] * o, fmaxf(acc[2 * i + 1], 0.f) * acc[half + 1 + 2 * i] * o);
        }
      };
      ffn_step(IC<2>(), IC<1>(), cB, 9, zero, nop, nop);
#pragma unroll 1
      for (int kb = 1; kb < 8; kb++)
        ffn_step(IC<1>(), IC<1>(), cB, 9 + kb, kb, nop, [&] {
          if (kb == 4 + wg) {
            mbar_wait(bars + 8 * B_G, 0);
            const uint32_t gb0 = *(const uint32_t*)(smem + OFF_G + (wg * 64 + w * 16 + g) * 4), gb1 = *(const uint32_t*)(smem + OFF_G + (wg * 64 + w * 16 + g + 8) * 4);
            tag = gb0 & 1; g0 = __uint_as_float(gb0 & ~1u); g1 = __uint_as_float(gb1 & ~1u);
            glu(cA, 32, 0, 0, 8);
          } else if (kb == 6 + wg) glu(cA, 32, 0, 8, 16);
        });
      if (tid == 0) PROF_EV(4);
      ffn_step(IC<0>(), IC<1>(), cC, 17, 0, nop, nop);
#pragma unroll 1
      for (int kb = 1; kb < 8; kb++)
        ffn_step(IC<1>(), IC<1>(), cC, 17 + kb, kb, nop, [&] {
          if (kb == 1 + wg) glu(cB, 32, 16, 0, 8);
          else if (kb == 3 + wg) glu(cB, 32, 16, 8, 16);
        });
      if (tid == 0) PROF_EV(5);
      auto m_step = [&](auto first, int i) {
        acquire(25 + i);
        wg_fence();
        const uint64_t dx = d128(dX + i * 2048), dm = d64(dN + RING + rslot(25 + i) * 1024);
        mma_ss64<0, 1, decltype(first)::value>(ct, dx, dm);
#pragma unroll
        for (int k = 1; k < MSPLIT; k++) mma_ss64<0, 1, 1>(ct, dx + ((k >> 2) * 1024 + (k & 3) * 2), dm + k * 64);
        wg_commit();
        wg_wait<1>();
        mbar_arrive_if(rel && i < 3, bars + 8 * (B_EA + rslot(24 + i)));
        mbar_arrive_if(elect && i, bars + 8 * (B_ET + i - 1));
        wg_fence();
#pragma unroll
        for (int k = MSPLIT; k < 8; k++) mma_ss64<0, 1, 1>(ct, dx + ((k >> 2) * 1024 + (k & 3) * 2), dm + k * 64);
        wg_commit();
      };
      auto freeT = [&](int t) { mbar_arrive_if(elect, bars + 8 * (B_ET + t)); };
      m_step(IC<0>(), 0);
#pragma unroll 1
      for (int i = 1; i < 5; i++) {
        if (i == 1 + wg) glu(cC, 32, 32, 0, 8);
        else if (i == 3 + wg) glu(cC, 32, 32, 8, 16);
        if (i < 4) m_step(IC<1>(), i);
      }
      waitA(29 + wg);
      if (tid == 0) PROF_EV(6);
      if (tid == 128) PROF_EV(27);
      mbar_wait(bars + 8 * (j == 0 ? B_T : B_TL), 0);
      if (tid == 0) PROF_EV(7);
      wg_fence();
      {
        const uint64_t dt = d128(dN + (OFF_T >> 4) + wg * 512), de = d128(dK + RING + (1 + wg) * 1024);
        mma_ss64<0, 1, 0>(ci, de, dt);
        mma_ss64<32, 1, 0>(ci, de + 512, dt);
#pragma unroll
        for (int k = 1; k < 4; k++) {
          mma_ss64<0, 1, 1>(ci, de + k * 2, dt + k * 128);
          mma_ss64<32, 1, 1>(ci, de + (512 + k * 2), dt + k * 128);
        }
        wg_commit();
        wg_wait<1>();
        freeT(3);
        fence_regs<0, 32>(ct);
        glu(ct, 16, 48, 0, 8);
      }

      auto twait = [&](uint32_t bar, uint32_t par, int) { mbar_wait(bar, par); };
      auto fetch = [&](uint4 (&pv)[4], int z) {
        twait(bars + 8 * (z < 4 ? B_Z + 2 * z + wg : B_HP + z - 4), 0, 8 + z);
        const uint8_t* src = smem + (z < 4 ? OFF_Z + z * U : (z - 4) * U) + tid * 16;
#pragma unroll
        for (int i = 0; i < 4; i++) pv[i] = *(const uint4*)(src + i * 4096);
      };
      auto check = [&](uint4 (&pv)[4], int z) {
        const uint32_t t0 = (uint32_t)clock();
        while (__any_sync(0xffffffffu, ((pv[0].x ^ tag) | (pv[1].x ^ tag) | (pv[2].x ^ tag) | (pv[3].x ^ tag)) & 1)) {
#pragma unroll
          for (int i = 0; i < 4; i++) pv[i] = ld_x4(g_part + (size_t)((rb * 8 + j) * 3 + z - 4) * 1024 + tid + i * 256);
          spin_guard(t0);
        }
#pragma unroll
        for (int i = 0; i < 4; i++) pv[i].x &= ~1u;
      };
      auto head = [&](auto off, int t, bool init) {
        constexpr int O = decltype(off)::value;
        twait(bars + 8 * (B_FT + (t & 3)), t >> 2, t);
        const uint64_t db = d128(dN + (t & 3) * (TB >> 4) + rank * 256);
        wg_fence();
        mma_rs64<O, 1, 2>(ct, h[0], h[1], h[2], h[3], db, zero + init);
#pragma unroll
        for (int k = 1; k < 6; k++) mma_rs64<O, 1, 1>(ct, h[4 * k], h[4 * k + 1], h[4 * k + 2], h[4 * k + 3], db + k * 128);
        wg_commit();
        wg_wait<1>();
      };
      auto rest = [&](auto off, int t, int z) {
        constexpr int O = decltype(off)::value, P = 32 - O;
        const uint64_t db = d128(dN + (t & 3) * (TB >> 4)), dw = db + rank * 256, dm = db + (rank ? 0 : 1536);
        wg_fence();
#pragma unroll
        for (int k = 6; k < 12; k++) mma_rs64<O, 1, 1>(ct, h[4 * k], h[4 * k + 1], h[4 * k + 2], h[4 * k + 3], dw + k * 128);
        wg_commit();
        uint4 pv[4];
        if (z >= 0) fetch(pv, z);
        wg_fence();
#pragma unroll
        for (int k = 0; k < 2; k++) mma_rs64<O, 1, 1>(ct, h[48 + 4 * k], h[49 + 4 * k], h[50 + 4 * k], h[51 + 4 * k], dm + k * 128);
#pragma unroll
        for (int k = 0; k < 4; k++) mma_rs64<O, 1, 1>(ct, yf[4 * k], yf[4 * k + 1], yf[4 * k + 2], yf[4 * k + 3], db + (14 + k) * 128);
        wg_commit();
        if (z >= 0) {
          if (z >= 4) check(pv, z);
#pragma unroll
          for (int i = 0; i < 4; i++) {
            const uint32_t a[4] = {pv[i].x, pv[i].y, pv[i].z, pv[i].w};
#pragma unroll
            for (int e = 0; e < 4; e++) { ct[P + 8 * i + 2 * e] = bf_lo(a[e]); ct[P + 8 * i + 2 * e + 1] = bf_hi(a[e]); }
          }
        }
      };
      const uint32_t peerZ = mapa(sb + OFF_Z + tid * 16, rank ^ 1), peerB = mapa(bars + 8 * (B_Z + wg), rank ^ 1);
      auto send = [&](auto off, int t) {
        constexpr int O = decltype(off)::value;
        fence_regs<O, 32>(ct);
        const bool grid = t >= 3 && t < 6;
        const int z = grid ? t - 3 : t == 6 ? 3 : t;
        uint32_t pk[16];
#pragma unroll
        for (int i = 0; i < 16; i++) pk[i] = pack_bf16(ct[O + 2 * i], ct[O + 2 * i + 1]);
        if (grid) {
          const int owner = rb * 8 + 2 * ((q4 + z + 1) & 3) + rank;
          uint4* dst = g_part + (size_t)(owner * 3 + z) * 1024 + tid;
#pragma unroll
          for (int i = 0; i < 4; i++) st_x4(dst + i * 256, (pk[4 * i] & ~1u) | tag, pk[4 * i + 1], pk[4 * i + 2], pk[4 * i + 3]);
          __syncwarp();
          hint_add_if(lane == 0, &g_cntP[32 * owner + z]);
        } else {
#pragma unroll
          for (int i = 0; i < 4; i++)
            asm volatile("st.async.weak.shared::cluster.mbarrier::complete_tx::bytes.v4.b32 [%0], {%1,%2,%3,%4}, [%5];" ::"r"(peerZ + z * U + i * 4096),
                         "r"(pk[4 * i]), "r"(pk[4 * i + 1]), "r"(pk[4 * i + 2]), "r"(pk[4 * i + 3]), "r"(peerB + 16 * z) : "memory");
        }
      };
      asm volatile("barrier.cluster.wait.aligned;" ::: "memory");
      head(IC<0>(), 0, false);
      if (elect) asm volatile("mbarrier.arrive.shared::cluster.b64 _, [%0];" ::"r"(mapa(bars + 8 * B_RDY, rank ^ 1)) : "memory");
      fence_regs<0, 64>(ci);
#pragma unroll
      for (int i = 0; i < 16; i++) {
        const float gg = ((i & 1) ? g1 : g0) * (2.0f / (2048.0f * 512.0f));
        if (i & 2) yf[i] = pack_pin((ci[2 * i] - ci[28 + 2 * i]) * gg, (ci[2 * i + 1] - ci[29 + 2 * i]) * gg);
        else yf[i] = pack_pin((ci[2 * i] + ci[36 + 2 * i]) * gg, (ci[2 * i + 1] + ci[37 + 2 * i]) * gg);
      }
      if (tid == 0) PROF_EV(8);
      if (tid == 128) PROF_EV(28);
#pragma unroll 1
      for (int t = 0;; t += 2) {
        rest(IC<0>(), t, t - 2);
        head(IC<32>(), t + 1, t >= 2);
        mbar_arrive_if(elect && t < 6, bars + 8 * (B_ET + t));
        if (t == 0) twait(bars + 8 * B_RDY, 0, 15);
        send(IC<0>(), t);
        rest(IC<32>(), t + 1, (t & 2) ? t - 1 : -1);
        if (t == 6) break;
        head(IC<0>(), t + 2, t == 2);
        mbar_arrive_if(elect, bars + 8 * (B_ET + t + 1));
        send(IC<32>(), t + 1);
      }
      if (tid == 0) PROF_EV(9);
      if (tid == 128) PROF_EV(29);
      {
        float (&sum)[64] = ct;
        uint4 p2[4], p3[4];
        fetch(p3, 3);
        if (tid == 0) PROF_EV(25);
        fetch(p2, 6);
        if (tid == 0) PROF_EV(24);
        check(p2, 6);
#pragma unroll
        for (int i = 0; i < 4; i++) {
          const uint32_t b[4] = {p2[i].x, p2[i].y, p2[i].z, p2[i].w}, c[4] = {p3[i].x, p3[i].y, p3[i].z, p3[i].w};
#pragma unroll
          for (int e = 0; e < 4; e++) {
            sum[8 * i + 2 * e] += bf_lo(c[e]) + bf_lo(b[e]);
            sum[8 * i + 2 * e + 1] += bf_hi(c[e]) + bf_hi(b[e]);
          }
        }
        if (tid == 0) PROF_EV(14);
        wg_wait<0>();
        fence_regs<32, 32>(ct);
#pragma unroll
        for (int i = 0; i < 32; i++) sum[i] += ct[32 + i];
        const uint32_t stg = sb + OFF_T + warp * 2048;
        const int mr = (lane & 7) + ((lane >> 3) & 1) * 8, mc = lane >> 4;
#pragma unroll
        for (int i = 0; i < 4; i++) {
          const uint32_t a = stg + mr * 128 + (((2 * i + mc) ^ (mr & 7)) << 4);
          asm volatile("stmatrix.sync.aligned.m8n8.x4.shared.b16 [%0], {%1,%2,%3,%4};" ::"r"(a), "r"(pack_bf16(sum[8 * i], sum[8 * i + 1])),
                       "r"(pack_bf16(sum[8 * i + 2], sum[8 * i + 3])), "r"(pack_bf16(sum[8 * i + 4], sum[8 * i + 5])),
                       "r"(pack_bf16(sum[8 * i + 6], sum[8 * i + 7])) : "memory");
        }
        asm volatile("fence.proxy.async.shared::cta;" ::: "memory");
        __syncwarp();
        if (elect_one()) {
          asm volatile("cp.async.bulk.tensor.3d.global.shared::cta.bulk_group [%0, {%2, %3, %4}], [%1];" ::"l"(&maps.o), "r"(stg), "r"(64 * j),
                       "r"(16 * w), "r"(2 * rb + wg) : "memory");
          asm volatile("cp.async.bulk.commit_group;\ncp.async.bulk.wait_group.read 0;" ::: "memory");
        }
      }
      if (tid == 0) { PROF_EV(15); PROF_CK(41); }
      if (tid == 128) PROF_EV(30);
    }
  } else if (warp < 12) {
    asm volatile("setmaxnreg.dec.sync.aligned.u32 104;");
    asm volatile("barrier.cluster.arrive.relaxed.aligned;" ::: "memory");
    const int t = tid - 256, w = warp - 8;
    const uint32_t ep = ld_x1(&g_epoch[blockIdx.x * 8]);
    const uint32_t tag = (ep + 1) & 1;
    auto w_issue = [&](const CUtensorMap* m) {
          if (elect_one()) { mbar_expect_tx(bars + 8 * (B_WR + w), 3072); tma4d(sb + OFF_T + w * 3072, m, bars + 8 * (B_WR + w), 16 * kg, 0, 2 * w, tn); }
          __syncwarp();
    };
    auto gate_rows = [&] {
      const int r = 16 * j + 4 * w + (lane >> 3);
      const uint4* pg = (const uint4*)gate_w + (lane & 7);
      {
        float a = 0.f;
        asm volatile("bar.sync 4, 256;" ::: "memory");
#pragma unroll 1
        for (int hf = 0; hf < 2; hf++) {
          uint4 v[4], u[4];
#pragma unroll
          for (int kb = 0; kb < 4; kb++) v[kb] = __ldg(pg + (4 * hf + kb) * 8);
          mbar_wait(bars + 8 * (B_FE + 1 + 2 * hf), 0);
          if (hf) w_issue(&maps.wr);
#pragma unroll
          for (int kb = 0; kb < 4; kb++) u[kb] = *(const uint4*)(smem + (4 * hf + kb) * U + r * 128 + (((lane ^ r) & 7) << 4));
#pragma unroll
          for (int kb = 0; kb < 4; kb++) {
            a = fmaf(bf_lo(u[kb].x), bf_lo(v[kb].x), a); a = fmaf(bf_hi(u[kb].x), bf_hi(v[kb].x), a);
            a = fmaf(bf_lo(u[kb].y), bf_lo(v[kb].y), a); a = fmaf(bf_hi(u[kb].y), bf_hi(v[kb].y), a);
            a = fmaf(bf_lo(u[kb].z), bf_lo(v[kb].z), a); a = fmaf(bf_hi(u[kb].z), bf_hi(v[kb].z), a);
            a = fmaf(bf_lo(u[kb].w), bf_lo(v[kb].w), a); a = fmaf(bf_hi(u[kb].w), bf_hi(v[kb].w), a);
          }
        }
#pragma unroll
        for (int o = 4; o; o >>= 1) a += __shfl_xor_sync(0xffffffffu, a, o);
        if ((lane & 7) == 0)
          asm volatile("st.relaxed.gpu.global.f32 [%0], %1;" ::"l"(g_gate + rb * 128 + r), "f"(tagf(__fdividef(1.0f, 1.0f + __expf(-a)), tag)) : "memory");
        if (t == 0) PROF_EV(18);
      }
    };
    {
      const int g = lane >> 2, q = lane & 3;
      uint32_t wf[32];
      if (!helper) {
        gate_rows();
        const uint32_t wa = sb + OFF_T + w * (3072 + 4) + q * 48 + g * 2;
#pragma unroll 1
        for (int ri = 0; ri < 2; ri++) {
          mbar_wait(bars + 8 * (B_WR + w), ri);
#pragma unroll
          for (int n2 = 0; n2 < NOLDS; n2++) {
            uint32_t v[16];
#pragma unroll
            for (int i = 0; i < 16; i++)
              asm volatile("ld.shared.u16 %0, [%1];" : "=r"(v[i]) : "r"(wa + (4 * n2 + ((i >> 1) & 3)) * 192 + (i & 1) * (1536 + 2) + (i >> 3) * 16) : "memory");
#pragma unroll
            for (int i = 0; i < 16; i++) {
              uint32_t& d = wf[(i >> 3) * 16 + 8 * n2 + (i & 7)];
              d = __byte_perm(d, v[i], 0x5432);
              asm volatile("" : "+r"(d)::"memory");
            }
          }
          __syncwarp();
          if (ri == 0) w_issue(&maps.wi);
        }
        asm volatile("bar.sync 1, 128;" ::: "memory");
        if (t == 0) PROF_EV(11);
      } else {
        asm volatile("bar.sync 4, 256;" ::: "memory");
        hint_wait(&g_cntW[0], (ep + 1) * 128u);
        const uint32_t t0 = (uint32_t)clock();
#pragma unroll 1
        for (;;) {
          uint32_t bad = 0;
#pragma unroll
          for (int i = 0; i < 32; i++) {
            const float2 v = ld_x2((const float2*)g_Wh + (i >> 4) * 2048 + 16 * w + g + 8 * (i & 1) + 64 * q + ((i >> 1) & 7) * 256);
            wf[i] = __float_as_uint(v.x); bad |= __float_as_uint(v.y) ^ tag;
          }
          if (!__any_sync(0xffffffffu, bad & 1)) break;
          spin_guard(t0);
        }
        if (t == 0) PROF_EV(11);
      }
      if (w == 0 && elect_one()) { mbar_expect_tx(bars + 8 * B_W, 8192); bulk_load(sb + OFF_D, g_DT.v, 8192, bars + 8 * B_W); }
      if (!helper) {
        const uint32_t t0 = (uint32_t)clock();
        uint32_t v;
        do { v = ld_x1(g_gate + rb * 128 + t); spin_guard(t0); } while (__any_sync(0xffffffffu, (v ^ tag) & 1));
        *(uint32_t*)(smem + OFF_G + t * 4) = v;
        __syncwarp();
        mbar_arrive_if(lane == 0, bars + 8 * B_G);
      }
      mbar_wait(bars + 8 * B_W, 0);
      mbar_wait(bars + 8 * B_HX, 0);
      if (t == 0) PROF_EV(12);
      const uint32_t dd = (sb & 0x3FFFF) >> 4;
      const uint64_t dF = d128((dd + (OFF_D >> 4)) | (512u << 16)), dI = d128((dd + (OFF_D >> 4)) | (1u << 16)), dA = d128((dd + (OFF_XB >> 4)) | (512u << 16));
      float az[32];
      const int zero = blockIdx.x >> 16;
      uint32_t pf[32];
#pragma unroll
      for (int mt = 0; mt < 2; mt++) {
        wg_fence();
        if (mt == 0) mma_ss64<0, 3, 0>(az, dA, dF);
        else mma_ss64<0, 3, 2>(az, dA + 512, dF, zero);
#pragma unroll
        for (int k = 1; k < 4; k++) mma_ss64<0, 3, 1>(az, dA + (mt * 512 + k * 128), dF + k * 128);
        wg_commit();
        wg_wait<0>();
        fence_regs<0, 32>(az);
#pragma unroll
        for (int i = 0; i < 16; i++) {
          const float wr = bf_lo(wf[16 * mt + i]), wi = bf_hi(wf[16 * mt + i]);
          pf[16 * mt + i] = pack_pin(fmaf(az[2 * i], wr, -az[2 * i + 1] * wi), fmaf(az[2 * i], wi, az[2 * i + 1] * wr));
        }
      }
      if (t == 0) PROF_EV(16);
#pragma unroll
      for (int mt = 0; mt < 2; mt++) {
        wg_fence();
        mma_rs64<0, 0, 2>(az, pf[16 * mt], pf[16 * mt + 1], pf[16 * mt + 2], pf[16 * mt + 3], dI, mt ? (int)helper : zero);
#pragma unroll
        for (int k = 1; k < 4; k++) mma_rs64<0, 0, 1>(az, pf[16 * mt + 4 * k], pf[16 * mt + 4 * k + 1], pf[16 * mt + 4 * k + 2], pf[16 * mt + 4 * k + 3], dI + k * 2);
        wg_commit();
        wg_wait<0>();
        fence_regs<0, 32>(az);
        if (!helper) {
          const int m = lane >> 3, r = lane & 7;
          const int sl = 2 * (m >> 1) + ((r >> 1) & 1) + 4 * (r >> 2);
          const uint32_t a0 = sb + OFF_XB + (2 * w + (m & 1)) * 2048 + sl * 64 + (((mt * 2 + (r & 1)) ^ (sl >> 1)) << 4);
#pragma unroll
          for (int i = 0; i < 4; i++)
            stsm4t(a0 + i * 512, pack_bf16(az[8 * i], az[8 * i + 1]), pack_bf16(az[8 * i + 2], az[8 * i + 3]), pack_bf16(az[8 * i + 4], az[8 * i + 5]),
                   pack_bf16(az[8 * i + 6], az[8 * i + 7]));
        }
      }
      if (helper) {
#pragma unroll
        for (int i = 0; i < 16; i++) {
          const int n = i >> 1, s0 = 8 * (n >> 1) + 2 * (n & 1) + (q & 1) + 4 * (q >> 1);
          if ((n & 1) == (int)(blockIdx.x & 1)) st_u2(g_Ts + s0 * 64 + 16 * w + g + 8 * (i & 1), pack_bf16(az[2 * i], az[2 * i + 1]), tag);
        }
        __syncwarp();
        hint_add_if(lane == 0, &g_cntH[0]);
        if (t == 0) { g_epoch[blockIdx.x * 8] = ep + 1; PROF_EV(13); }
      } else {
        asm volatile("fence.proxy.async.shared::cta;" ::: "memory");
        __syncwarp();
        if (elect_one()) {
          if (t == 0) PROF_EV(17);
          if (SPACE) __nanosleep(SPACE * w);
          asm volatile("cp.async.bulk.tensor.3d.global.shared::cta.bulk_group [%0, {%2, %3, %4}], [%1];" ::"l"(&maps.ts), "r"(sb + OFF_XB + w * 4096),
                       "r"(32 * kg), "r"(0), "r"(8 * tn + 2 * w) : "memory");
          bulk_done_signal(&g_cntT[32 * j]);
          if (t == 96) PROF_EV(13);
        }
        __syncwarp();
        if (j == 0) {
          hint_wait(&g_cntH[0], (ep + 1) * 8u);
          const uint32_t t0 = (uint32_t)clock();
          float2 v;
          do { v = ld_x2((const float2*)g_Ts + 2 * rb * 64 + t); spin_guard(t0); } while (__any_sync(0xffffffffu, (__float_as_uint(v.y) ^ tag) & 1));
          mbar_wait(bars + 8 * B_TL, 0);
          const uint32_t u = __float_as_uint(v.x);
          *(uint16_t*)(smem + OFF_T + t * 128 + ((t & 7) << 4)) = (uint16_t)u;
          *(uint16_t*)(smem + OFF_T + t * 128 + (((t & 7) ^ 1) << 4)) = (uint16_t)(u >> 16);
          asm volatile("fence.proxy.async.shared::cta;" ::: "memory");
          __syncwarp();
          mbar_arrive_if(lane == 0, bars + 8 * B_T);
        }
      }
    }
  } else {
    asm volatile("setmaxnreg.dec.sync.aligned.u32 24;");
    auto xf_load = [&](int q) {
      const uint32_t fb = bars + 8 * (B_FX + q);
      mbar_expect_tx(fb, U + 8192);
      tma3d(sb + q * U, &maps.x, fb, 64 * q, 0, 2 * rb);
      if (q >= 4) mbar_wait(bars + 8 * (B_FE + ((q - 4) >> 1)), 0);
      tma2d(sb + OFF_XB + (q & 3) * 8192, &maps.ft, fb, 64 * q, 64 * j);
    };
    if (elect_one()) {
      if (warp == 14) {
#pragma unroll
        for (int i = 0; i < B_FT; i++) mbar_init(bars + 8 * i, 1);
        asm volatile("fence.proxy.async.shared::cta;" ::: "memory");
        if (!helper) {
#pragma unroll 1
          for (int n = 0; n < 2; n++) {
            const uint32_t fb = bars + 8 * (B_FA + n);
            xf_load(2 * n); xf_load(2 * n + 1);
            mbar_expect_tx(fb, U);
            tma2d(sb + OFF_RING + n * U, &maps.g64, fb, f_full, 64 * n);
            tma2d(sb + OFF_RING + n * U + 8192, &maps.u64, fb, f_full, 64 * n);
          }
        }
      } else if (warp == 15) {
#pragma unroll
        for (int i = B_FT; i < NBAR; i++) mbar_init(bars + 8 * i, i < B_EA ? 1 : i < B_T ? 2 : 4);
#pragma unroll
        for (int i = 0; i < 8; i++) mbar_expect_tx(bars + 8 * (B_Z + i), U / 2);
        asm volatile("fence.mbarrier_init.release.cluster;" ::: "memory");
        asm volatile("fence.proxy.async.shared::cta;" ::: "memory");
      } else if (warp == 13) {
#pragma unroll
        for (int i = 1; i < 4; i++) asm volatile("prefetch.tensormap [%0];" ::"l"((const char*)&maps + i * 128) : "memory");
      }
    }
    __syncwarp();
    asm volatile("bar.arrive 0, 384;" ::: "memory");
    asm volatile("bar.arrive 4, 256;" ::: "memory");
    __syncwarp();
    asm volatile("barrier.cluster.arrive.relaxed.aligned;" ::: "memory");
    asm volatile("bar.sync 3, 128;" ::: "memory");
    if (warp == 15 && !helper) {
        mbar_wait(bars + 8 * B_FE, 0);
        const uint32_t tag = (ld_x1(&g_epoch[blockIdx.x * 8]) + 1) & 1;
        const int c = lane >> 4, jj = 16 * blockIdx.x + (lane & 15), jm = (2048 - jj) & 2047;
        const unsigned short* pr = (const unsigned short*)w_r + 256 * c;
        const unsigned short* pi = (const unsigned short*)w_i + 256 * c;
        const float wr = 0.25f * (bf_lo(__ldg(pr + jj * 257)) + bf_lo(__ldg(pr + jm * 257)));
        const float wi = 0.25f * (bf_lo(__ldg(pi + jj * 257)) - bf_lo(__ldg(pi + jm * 257)));
        st_u2(g_Wh + c * 2048 + jj, c ? pack_bf16(-wi, wr) : pack_bf16(wr, wi), tag);
        __syncwarp();
        hint_add_if(lane == 0, &g_cntW[0]);
      }
    if ((!helper || warp == 15) && elect_one()) {
      if (warp < 14) {
        const int p = warp - 12;
#pragma unroll 1
        for (int n = 2; n < 31; n++) {
          const bool table = n == 4 || n >= 29;
          const int q = n < 4 ? n : n - 1;
          const CUtensorMap* m = table ? &maps.e : n >= 25 ? &maps.g32 + p : &maps.g64 + p;
          const int c0 = table ? 0 : n >= 25 ? f_half : f_full + 64 * (q >> 3);
          const int c1 = table ? (2 * rb + ((n & 1) ^ 1)) * 128 + 64 * p : n >= 25 ? 128 * (n - 25) : 64 * (q & 7);
          const uint32_t fb = bars + 8 * (B_FA + (n & 3)), dst = sb + OFF_RING + (n & 3) * U + p * 8192;
          if (n < 4) mbar_wait(bars + 8 * (B_FE + n - 2), 0);
          else mbar_wait(bars + 8 * (B_EA + (n & 3)), ((n >> 2) & 1) ^ 1);
          tma2d(dst, m, fb, c0, c1);
          if (p == 0) mbar_expect_tx(fb, U);
        }
      } else if (warp == 15) {
        const unsigned ep1 = ld_x1(&g_epoch[blockIdx.x * 8]) + 1;
        flag_wait(&g_cntX[helper ? 0 : 32 * j], ep1 * 16u);
        PROF_EV(22);
        mbar_expect_tx(bars + 8 * B_HX, U);
        bulk_load(sb + OFF_XB, g_X + (size_t)(helper ? 128 : kg * 8 + tn) * 8192, U, bars + 8 * B_HX);
        if (!helper) {
          flag_wait(&g_cntT[32 * j], ep1 * 64u);
          PROF_EV(23);
          mbar_expect_tx(bars + 8 * B_TL, U);
          tma3d(sb + OFF_T, &maps.t, bars + 8 * B_TL, 64 * j, 0, 2 * rb);
#pragma unroll 1
          for (int i = 0; i < 3; i++) {
            mbar_wait(bars + 8 * (B_PZ + (i >> 1)), 0);
            flag_wait(&g_cntP[32 * (rb * 8 + j) + i], ep1 * 8u);
            if (i == 2) PROF_EV(26);
            mbar_expect_tx(bars + 8 * (B_HP + i), U);
            bulk_load(sb + i * U, g_part + (size_t)((rb * 8 + j) * 3 + i) * 1024, U, bars + 8 * (B_HP + i));
          }
          g_epoch[blockIdx.x * 8] = ep1;
        }
      } else {
#pragma unroll 1
        for (int q = 4; q < 8; q++) xf_load(q);
        mbar_wait(bars + 8 * (B_FE + 2), 0);
        mbar_expect_tx(bars + 8 * B_E0, U);
        tma2d(sb + OFF_XB, &maps.e, bars + 8 * B_E0, 0, 2 * rb * 128);
        tma2d(sb + OFF_XB + 8192, &maps.e, bars + 8 * B_E0, 0, 2 * rb * 128 + 64);
#pragma unroll 1
        for (int h2 = 0; h2 < 2; h2++) {
          const int s0 = 2 * rb + h2, sg = (s0 & ~6) | ((s0 & 2) << 1) | ((s0 & 4) >> 1);
          mbar_wait(bars + 8 * (B_XS + h2), 0);
#pragma unroll 1
          for (int c = 0; c < 2; c++) {
            asm volatile("cp.async.bulk.tensor.4d.global.shared::cta.bulk_group [%0, {%2, %3, %4, %5}], [%1];" ::"l"(&maps.xs),
                         "r"(sb + OFF_XB + h2 * 8192 + c * 4096), "r"(0), "r"(sg), "r"(0), "r"(16 * j + 8 * c) : "memory");
            if (j == 0)
              asm volatile("cp.async.bulk.global.shared::cta.bulk_group [%0], [%1], 256;" ::"l"(g_X + 128 * 8192 + c * 4096 + sg * 128),
                           "r"(sb + OFF_SP + h2 * 512 + c * 256) : "memory");
            if (SPACE && h2 + c < 2) __nanosleep(SPACE);
          }
        }
        bulk_done_signal(&g_cntX[32 * j]);
        PROF_EV(20);
        asm volatile("prefetch.tensormap [%0];" ::"l"(&maps.o) : "memory");
#pragma unroll 1
        for (int t = 0; t < 8; t++) {
          const int i = t < 3 ? t + 1 : t < 6 ? t - 2 : 0;
          const int col = 64 * (2 * ((q4 + i) & 3) + ((t < 3 || t == 6) ? 1 - rank : rank));
          const uint32_t fb = bars + 8 * (B_FT + (t & 3)), dst = sb + (t & 3) * TB;
          mbar_wait(bars + 8 * (B_ET + (t == 2 ? 3 : t & 3)), t >> 2);
          mbar_expect_tx(fb, TB);
          tma2d(dst, &maps.d224, fb, col, 224 * j);
          if (t < 2) mbar_wait(bars + 8 * (B_ET + t + 1), 0);
          tma2d(dst + 28672, &maps.ft, fb, col, 64 * j);
        }
      }
    }
  }
}

typedef CUresult (*EncodeFn)(CUtensorMap*, CUtensorMapDataType, cuuint32_t, void*, const cuuint64_t*, const cuuint64_t*, const cuuint32_t*,
                             const cuuint32_t*, CUtensorMapInterleave, CUtensorMapSwizzle, CUtensorMapL2promotion, CUtensorMapFloatOOBfill);

static void encode(EncodeFn f, CUtensorMap* m, const void* base, int rank, const cuuint64_t* dims, const cuuint64_t* strides, const cuuint32_t* box,
                   CUtensorMapSwizzle sw) {
  cuuint32_t es[5] = {1, 1, 1, 1, 1};
  f(m, CU_TENSOR_MAP_DATA_TYPE_BFLOAT16, rank, (void*)base, dims, strides, box, es, CU_TENSOR_MAP_INTERLEAVE_NONE, sw,
    CU_TENSOR_MAP_L2_PROMOTION_L2_128B, CU_TENSOR_MAP_FLOAT_OOB_FILL_NONE);
}

extern "C" void kernel_launch(void* const* d_in, const int* in_sizes, int n_in, void* d_out, int out_size) {
  (void)in_sizes; (void)n_in; (void)out_size;
  const __nv_bfloat16* x = (const __nv_bfloat16*)d_in[0];
  const __nv_bfloat16* w_r = (const __nv_bfloat16*)d_in[1];
  const __nv_bfloat16* w_i = (const __nv_bfloat16*)d_in[2];
  const __nv_bfloat16* Wg = (const __nv_bfloat16*)d_in[4];
  const __nv_bfloat16* Wu = (const __nv_bfloat16*)d_in[5];
  const __nv_bfloat16* Wd = (const __nv_bfloat16*)d_in[6];
  const __nv_bfloat16* gw = (const __nv_bfloat16*)d_in[7];

  void* fp = nullptr; cudaDriverEntryPointQueryResult qr;
  cudaGetDriverEntryPoint("cuTensorMapEncodeTiled", &fp, cudaEnableDefault, &qr);
  EncodeFn enc = (EncodeFn)fp;
  void *pFT, *pET, *pX, *pT;
  cudaGetSymbolAddress(&pX, g_X); cudaGetSymbolAddress(&pT, g_T);
  cudaGetSymbolAddress(&pFT, g_FT); cudaGetSymbolAddress(&pET, g_ET);

  Maps mp;
  const CUtensorMapSwizzle S128 = CU_TENSOR_MAP_SWIZZLE_128B, S64 = CU_TENSOR_MAP_SWIZZLE_64B;
  { cuuint64_t d[3] = {512, 64, 32}, s[2] = {32768, 1024}; cuuint32_t b[3] = {64, 64, 2}, b2[3] = {64, 16, 1};
    encode(enc, &mp.x, x, 3, d, s, b, S128); encode(enc, &mp.o, d_out, 3, d, s, b2, S128); }
  { cuuint64_t d[2] = {512, 512}, s[1] = {1024}; cuuint32_t b[2] = {64, 64}; encode(enc, &mp.ft, pFT, 2, d, s, b, S128); }
  { cuuint64_t d[4] = {128, 32, 2, 129}, s[3] = {256, 8192, 16384}; cuuint32_t b[4] = {128, 1, 2, 8}; encode(enc, &mp.xs, pX, 4, d, s, b, CU_TENSOR_MAP_SWIZZLE_NONE); }
  { cuuint64_t d[3] = {512, 32, 64}, s[2] = {65536, 1024}; cuuint32_t b[3] = {32, 32, 2}; encode(enc, &mp.ts, pT, 3, d, s, b, S64); }
  { cuuint64_t d[3] = {512, 64, 32}, s[2] = {1024, 65536}; cuuint32_t b[3] = {64, 64, 2}; encode(enc, &mp.t, pT, 3, d, s, b, S128); }
  { cuuint64_t d[2] = {64, 4096}, s[1] = {128}; cuuint32_t b[2] = {64, 64}; encode(enc, &mp.e, pET, 2, d, s, b, S128); }
  { cuuint64_t d[2] = {1792, 512}, s[1] = {3584}; cuuint32_t b[2] = {64, 64}, b2[2] = {32, 128};
    encode(enc, &mp.g64, Wg, 2, d, s, b, S128); encode(enc, &mp.u64, Wu, 2, d, s, b, S128);
    encode(enc, &mp.g32, Wg, 2, d, s, b2, S64); encode(enc, &mp.u32, Wu, 2, d, s, b2, S64); }
  { cuuint64_t d[2] = {512, 1792}, s[1] = {1024}; cuuint32_t b[2] = {64, 224}; encode(enc, &mp.d224, Wd, 2, d, s, b, S128); }
  { cuuint64_t d[4] = {264, 32, 8, 8}, s[3] = {32896, 512, 4112}; cuuint32_t b[4] = {24, 32, 2, 1};
    encode(enc, &mp.wr, w_r, 4, d, s, b, CU_TENSOR_MAP_SWIZZLE_NONE); encode(enc, &mp.wi, w_i, 4, d, s, b, CU_TENSOR_MAP_SWIZZLE_NONE); }

  cudaFuncSetAttribute(fused_kernel, cudaFuncAttributeMaxDynamicSharedMemorySize, SMEM_BYTES);
  fused_kernel<<<NCTA, 512, SMEM_BYTES>>>(mp, w_r, w_i, gw);
}
```

```cpp
#include <cuda_runtime.h>
#include <cuda_bf16.h>
#include <cuda.h>
#include <stdint.h>

namespace tbl {
constexpr double PI = 3.14159265358979323846264338327950288;
constexpr double sin_s(double x) { double t = x, s = x; for (int n = 1; n < 12; n++) { t *= -x * x / ((2 * n) * (2 * n + 1)); s += t; } return s; }
constexpr double cos_s(double x) { double t = 1, s = 1; for (int n = 1; n < 12; n++) { t *= -x * x / ((2 * n - 1) * (2 * n)); s += t; } return s; }
constexpr double cos2048(int m) {
  m &= 2047; if (m > 1024) m = 2048 - m;
  bool neg = false; if (m > 512) { m = 1024 - m; neg = true; }
  double v = (m <= 256) ? cos_s(2 * PI * m / 2048) : sin_s(2 * PI * (512 - m) / 2048);
  return neg ? -v : v;
}
constexpr uint16_t to_bf16(double v) {
  if (v == 0) return 0;
  uint16_t s = 0; if (v < 0) { s = 0x8000; v = -v; }
  int e = 0; while (v >= 2) { v /= 2; e++; } while (v < 1) { v *= 2; e--; }
  double m = (v - 1) * 128; int mi = (int)m; double fr = m - mi;
  if (fr > 0.5 || (fr == 0.5 && (mi & 1))) mi++;
  if (mi == 128) { mi = 0; e++; }
  return (uint16_t)(s | ((e + 127) << 7) | mi);
}
struct CosT { uint16_t v[2048]; constexpr CosT() : v() { for (int i = 0; i < 2048; i++) v[i] = to_bf16(cos2048(i)); } };
struct alignas(1024) FT {
  uint16_t v[512 * 512];
  constexpr FT() : v() {
    CosT c;
    for (int r = 0; r < 512; r++) {
      int k = (r >> 4) * 8 + (r & 7), e = (r >> 3) & 1;
      int mul = 4 * k, add = e ? 512 : 0;
      if (k == 0 && e == 1) { mul = 1024; add = 0; }
      for (int d = 0; d < 512; d++) v[r * 512 + d] = c.v[(d * mul + add) & 2047];
    }
  }
};
struct alignas(1024) ET {
  uint16_t v[2048 * 128];
  constexpr ET() : v() {
    CosT c;
    for (int s = 0; s < 2048; s++)
      for (int j = 0; j < 64; j++) {
        const int o = (s & 31) * 8192 + (s >> 5) * 64 + j;
        v[o] = c.v[(s * j) & 2047]; v[o + 4096] = c.v[(s * j + 512) & 2047];
      }
  }
};
struct alignas(1024) DT {
  uint16_t v[64 * 64];
  constexpr DT() : v() {
    CosT c;
    for (int r = 0; r < 64; r++)
      for (int n = 0; n < 64; n++) {
        const int sg = r >> 1, s0 = (sg & ~6) | ((sg & 2) << 1) | ((sg & 4) >> 1), e = r & 1, f = n & 1;
        const int m = 64 * s0 * (n >> 1) + (e == f ? 0 : e ? -512 : 512);
        v[r * 64 + (((n >> 3) ^ (r & 7)) << 3) + (n & 7)] = c.v[m & 2047];
      }
  }
};
}

__device__ constexpr tbl::FT g_FT = tbl::FT();
__device__ constexpr tbl::ET g_ET = tbl::ET();
__device__ constexpr tbl::DT g_DT = tbl::DT();

struct alignas(1024) Work {
  unsigned epoch[132 * 8];
  unsigned cntX[8 * 32], cntT[8 * 32], cntP[128 * 32], cntW[32], cntH[32];
  alignas(16) float gate[16 * 128];
  alignas(16) uint2 Wh[2 * 2048];
  alignas(16) uint2 Ts[32 * 64];
  alignas(1024) uint16_t X[129 * 8192];
  alignas(1024) uint16_t T[32 * 64 * 512];
  alignas(1024) uint4 part[128 * 3 * 1024];
};
__device__ Work g_work;
#define PROF_EV(i) do {} while (0)
#define PROF_CK(i) do {} while (0)

__device__ __forceinline__ uint32_t smem_u32(const void* p) { return (uint32_t)__cvta_generic_to_shared(p); }
__device__ __forceinline__ void mbar_init(uint32_t bar, uint32_t cnt) { asm volatile("mbarrier.init.shared::cta.b64 [%0], %1;" ::"r"(bar), "r"(cnt)); }
__device__ __forceinline__ void mbar_expect_tx(uint32_t bar, uint32_t bytes) { asm volatile("mbarrier.arrive.expect_tx.shared::cta.b64 _, [%0], %1;" ::"r"(bar), "r"(bytes) : "memory"); }
__device__ __forceinline__ void mbar_arrive(uint32_t bar) { asm volatile("mbarrier.arrive.shared::cta.b64 _, [%0];" ::"r"(bar) : "memory"); }
__device__ __forceinline__ bool elect_one() {
  uint32_t p;
  asm volatile("{\n.reg .pred p;\nelect.sync _|p, 0xffffffff;\nselp.u32 %0, 1, 0, p;\n}" : "=r"(p));
  return p;
}
__device__ __forceinline__ void mbar_arrive_if(bool p, uint32_t bar) {
  asm volatile("{\n.reg .pred p;\nsetp.ne.b32 p, %1, 0;\n@p mbarrier.arrive.shared::cta.b64 _, [%0];\n}" ::"r"(bar), "r"((int)p) : "memory");
}
__device__ __forceinline__ void hint_add_if(bool p, unsigned* a) {
  asm volatile("{\n.reg .pred p;\nsetp.ne.b32 p, %1, 0;\n@p red.relaxed.gpu.global.add.u32 [%0], 1;\n}" ::"l"(a), "r"((int)p) : "memory");
}
__device__ __forceinline__ bool mbar_try(uint32_t bar, uint32_t parity) {
  uint32_t ok;
  asm volatile("{\n.reg .pred p;\nmbarrier.test_wait.parity.shared::cta.b64 p, [%1], %2;\nselp.u32 %0, 1, 0, p;\n}" : "=r"(ok) : "r"(bar), "r"(parity) : "memory");
  return ok;
}
__device__ __forceinline__ void mbar_wait(uint32_t bar, uint32_t parity) {
  asm volatile(
      "{\n.reg .pred p;\n.reg .u32 n;\nmov.u32 n, 0;\n"
      "W_LOOP:\nmbarrier.try_wait.parity.shared::cta.b64 p, [%0], %1;\n@p bra W_DONE;\n"
      "add.u32 n, n, 1;\nsetp.lt.u32 p, n, 0x40000;\n@p bra W_LOOP;\ntrap;\nW_DONE:\n}" ::"r"(bar), "r"(parity) : "memory");
}
__device__ __forceinline__ void bulk_load(uint32_t dst, const void* src, uint32_t bytes, uint32_t bar) {
  asm volatile("cp.async.bulk.shared::cluster.global.mbarrier::complete_tx::bytes [%0], [%1], %2, [%3];" ::"r"(dst), "l"(src), "r"(bytes), "r"(bar) : "memory");
}
__device__ __forceinline__ void cp16(uint32_t dst, const void* src) { asm volatile("cp.async.cg.shared.global [%0], [%1], 16;" ::"r"(dst), "l"(src) : "memory"); }
__device__ __forceinline__ void spin_guard(uint32_t t0) { if ((uint32_t)clock() - t0 > (1u << 30)) __trap(); }
__device__ __forceinline__ float tagf(float v, uint32_t tag) { return __uint_as_float((__float_as_uint(v) & ~1u) | tag); }
__device__ __forceinline__ float untag(float v) { return __uint_as_float(__float_as_uint(v) & ~1u); }
__device__ __forceinline__ void st_x2(float2* p, float a, float b) { asm volatile("st.relaxed.gpu.global.v2.f32 [%0], {%1,%2};" ::"l"(p), "f"(a), "f"(b) : "memory"); }
__device__ __forceinline__ float2 ld_x2(const float2* p) { float2 v; asm volatile("ld.relaxed.gpu.global.v2.f32 {%0,%1}, [%2];" : "=f"(v.x), "=f"(v.y) : "l"(p) : "memory"); return v; }
__device__ __forceinline__ void st_u2(uint2* p, uint32_t a, uint32_t b) { asm volatile("st.relaxed.gpu.global.v2.u32 [%0], {%1,%2};" ::"l"(p), "r"(a), "r"(b) : "memory"); }
__device__ __forceinline__ void prefetch2d(const CUtensorMap* m, int c0, int c1) { asm volatile("cp.async.bulk.prefetch.tensor.2d.L2.global [%0, {%1, %2}];" ::"l"(m), "r"(c0), "r"(c1) : "memory"); }
__device__ __forceinline__ void prefetch1d(const void* p, uint32_t bytes) { asm volatile("cp.async.bulk.prefetch.L2.global [%0], %1;" ::"l"(p), "r"(bytes) : "memory"); }
__device__ __forceinline__ uint32_t ld_x1(const void* p) { uint32_t v; asm volatile("ld.relaxed.gpu.global.u32 %0, [%1];" : "=r"(v) : "l"(p) : "memory"); return v; }
__device__ __forceinline__ uint4 ld_x4(const void* p) { uint4 v; asm volatile("ld.relaxed.gpu.global.v4.u32 {%0,%1,%2,%3}, [%4];" : "=r"(v.x), "=r"(v.y), "=r"(v.z), "=r"(v.w) : "l"(p) : "memory"); return v; }
__device__ __forceinline__ void st_x4(void* p, uint32_t a, uint32_t b, uint32_t c, uint32_t d) { asm volatile("st.relaxed.gpu.global.v4.u32 [%0], {%1,%2,%3,%4};" ::"l"(p), "r"(a), "r"(b), "r"(c), "r"(d) : "memory"); }
__device__ __forceinline__ uint32_t mapa(uint32_t a, uint32_t cta) { uint32_t r; asm volatile("mapa.shared::cluster.u32 %0, %1, %2;" : "=r"(r) : "r"(a), "r"(cta)); return r; }
__device__ __forceinline__ void stsm4t(uint32_t a, uint32_t r0, uint32_t r1, uint32_t r2, uint32_t r3) {
  asm volatile("stmatrix.sync.aligned.m8n8.x4.trans.shared.b16 [%0], {%1,%2,%3,%4};" ::"r"(a), "r"(r0), "r"(r1), "r"(r2), "r"(r3) : "memory");
}
__device__ __forceinline__ void hint_add(unsigned* p) { asm volatile("red.relaxed.gpu.global.add.u32 [%0], 1;" ::"l"(p) : "memory"); }
__device__ __forceinline__ void hint_wait(const unsigned* p, unsigned target) {
  const uint32_t t0 = (uint32_t)clock();
  while ((int)(ld_x1(p) - target) < 0) spin_guard(t0);
}
__device__ __forceinline__ void bulk_done_signal(unsigned* p) {
  asm volatile("cp.async.bulk.commit_group;\ncp.async.bulk.wait_group 0;\nfence.proxy.async.global;" ::: "memory");
  hint_add(p);
}
__device__ __forceinline__ void flag_wait(const unsigned* p, unsigned target) {
  hint_wait(p, target);
  asm volatile("fence.proxy.async.global;" ::: "memory");
}
__device__ __forceinline__ void tma2d(uint32_t dst, const CUtensorMap* m, uint32_t bar, int c0, int c1) {
  asm volatile("cp.async.bulk.tensor.2d.shared::cluster.global.mbarrier::complete_tx::bytes [%0], [%1, {%3, %4}], [%2];" ::"r"(dst), "l"(m), "r"(bar), "r"(c0), "r"(c1) : "memory");
}
__device__ __forceinline__ void tma3d(uint32_t dst, const CUtensorMap* m, uint32_t bar, int c0, int c1, int c2) {
  asm volatile("cp.async.bulk.tensor.3d.shared::cluster.global.mbarrier::complete_tx::bytes [%0], [%1, {%3, %4, %5}], [%2];" ::"r"(dst), "l"(m), "r"(bar), "r"(c0), "r"(c1), "r"(c2) : "memory");
}
__device__ __forceinline__ void tma4d(uint32_t dst, const CUtensorMap* m, uint32_t bar, int c0, int c1, int c2, int c3) {
  asm volatile("cp.async.bulk.tensor.4d.shared::cluster.global.mbarrier::complete_tx::bytes [%0], [%1, {%3, %4, %5, %6}], [%2];" ::"r"(dst), "l"(m), "r"(bar), "r"(c0), "r"(c1), "r"(c2), "r"(c3) : "memory");
}
__device__ __forceinline__ void wg_fence() { asm volatile("wgmma.fence.sync.aligned;" ::: "memory"); }
__device__ __forceinline__ void wg_commit() { asm volatile("wgmma.commit_group.sync.aligned;" ::: "memory"); }
template <int N> __device__ __forceinline__ void wg_wait() { asm volatile("wgmma.wait_group.sync.aligned %0;" ::"n"(N) : "memory"); }
template <int O, int N, int NN> __device__ __forceinline__ void fence_regs(float (&d)[NN]) {
#pragma unroll
  for (int i = 0; i < N; i++) asm volatile("" : "+f"(d[O + i])::"memory");
}
__device__ __forceinline__ uint32_t pack_bf16(float lo, float hi) {
  uint32_t r; asm("cvt.rn.bf16x2.f32 %0, %1, %2;" : "=r"(r) : "f"(hi), "f"(lo)); return r;
}
__device__ __forceinline__ uint32_t pack_pin(float lo, float hi) {
  uint32_t r; asm volatile("cvt.rn.bf16x2.f32 %0, %1, %2;" : "=r"(r) : "f"(hi), "f"(lo) : "memory"); return r;
}
__device__ __forceinline__ float bf_lo(uint32_t u) { return __uint_as_float(u << 16); }
__device__ __forceinline__ float bf_hi(uint32_t u) { return __uint_as_float(u & 0xffff0000u); }

__device__ __forceinline__ uint64_t d128(uint32_t lo) { uint64_t d; asm("mov.b64 %0, {%1, 0x40000040};" : "=l"(d) : "r"(lo)); return d; }
__device__ __forceinline__ uint64_t d64(uint32_t lo) { uint64_t d; asm("mov.b64 %0, {%1, 0x80000020};" : "=l"(d) : "r"(lo)); return d; }
template<int O,int TB,int ACC,int NN> __device__ __forceinline__ void mma_ss64(float (&d)[NN], uint64_t da, uint64_t db, int sd = 0){
  if constexpr (ACC == 1) asm volatile("wgmma.mma_async.sync.aligned.m64n64k16.f32.bf16.bf16 {%0,%1,%2,%3,%4,%5,%6,%7,%8,%9,%10,%11,%12,%13,%14,%15,%16,%17,%18,%19,%20,%21,%22,%23,%24,%25,%26,%27,%28,%29,%30,%31}, %32, %33, 1, 1, 1, %35, %34;"
   : "+f"(d[O+0]), "+f"(d[O+1]), "+f"(d[O+2]), "+f"(d[O+3]), "+f"(d[O+4]), "+f"(d[O+5]), "+f"(d[O+6]), "+f"(d[O+7]), "+f"(d[O+8]), "+f"(d[O+9]), "+f"(d[O+10]), "+f"(d[O+11]), "+f"(d[O+12]), "+f"(d[O+13]), "+f"(d[O+14]), "+f"(d[O+15]), "+f"(d[O+16]), "+f"(d[O+17]), "+f"(d[O+18]), "+f"(d[O+19]), "+f"(d[O+20]), "+f"(d[O+21]), "+f"(d[O+22]), "+f"(d[O+23]), "+f"(d[O+24]), "+f"(d[O+25]), "+f"(d[O+26]), "+f"(d[O+27]), "+f"(d[O+28]), "+f"(d[O+29]), "+f"(d[O+30]), "+f"(d[O+31])
   : "l"(da), "l"(db), "n"(TB & 1), "n"(TB >> 1));
  else if constexpr (ACC == 0) asm volatile("wgmma.mma_async.sync.aligned.m64n64k16.f32.bf16.bf16 {%0,%1,%2,%3,%4,%5,%6,%7,%8,%9,%10,%11,%12,%13,%14,%15,%16,%17,%18,%19,%20,%21,%22,%23,%24,%25,%26,%27,%28,%29,%30,%31}, %32, %33, 0, 1, 1, %35, %34;"
   : "=f"(d[O+0]), "=f"(d[O+1]), "=f"(d[O+2]), "=f"(d[O+3]), "=f"(d[O+4]), "=f"(d[O+5]), "=f"(d[O+6]), "=f"(d[O+7]), "=f"(d[O+8]), "=f"(d[O+9]), "=f"(d[O+10]), "=f"(d[O+11]), "=f"(d[O+12]), "=f"(d[O+13]), "=f"(d[O+14]), "=f"(d[O+15]), "=f"(d[O+16]), "=f"(d[O+17]), "=f"(d[O+18]), "=f"(d[O+19]), "=f"(d[O+20]), "=f"(d[O+21]), "=f"(d[O+22]), "=f"(d[O+23]), "=f"(d[O+24]), "=f"(d[O+25]), "=f"(d[O+26]), "=f"(d[O+27]), "=f"(d[O+28]), "=f"(d[O+29]), "=f"(d[O+30]), "=f"(d[O+31])
   : "l"(da), "l"(db), "n"(TB & 1), "n"(TB >> 1));
  else asm volatile("{\n.reg .pred p;\nsetp.ne.b32 p, %36, 0;\nwgmma.mma_async.sync.aligned.m64n64k16.f32.bf16.bf16 {%0,%1,%2,%3,%4,%5,%6,%7,%8,%9,%10,%11,%12,%13,%14,%15,%16,%17,%18,%19,%20,%21,%22,%23,%24,%25,%26,%27,%28,%29,%30,%31}, %32, %33, p, 1, 1, %35, %34;\n}"
   : "+f"(d[O+0]), "+f"(d[O+1]), "+f"(d[O+2]), "+f"(d[O+3]), "+f"(d[O+4]), "+f"(d[O+5]), "+f"(d[O+6]), "+f"(d[O+7]), "+f"(d[O+8]), "+f"(d[O+9]), "+f"(d[O+10]), "+f"(d[O+11]), "+f"(d[O+12]), "+f"(d[O+13]), "+f"(d[O+14]), "+f"(d[O+15]), "+f"(d[O+16]), "+f"(d[O+17]), "+f"(d[O+18]), "+f"(d[O+19]), "+f"(d[O+20]), "+f"(d[O+21]), "+f"(d[O+22]), "+f"(d[O+23]), "+f"(d[O+24]), "+f"(d[O+25]), "+f"(d[O+26]), "+f"(d[O+27]), "+f"(d[O+28]), "+f"(d[O+29]), "+f"(d[O+30]), "+f"(d[O+31])
   : "l"(da), "l"(db), "n"(TB & 1), "n"(TB >> 1), "r"(sd));
}
template<int O,int TB,int ACC,int NN> __device__ __forceinline__ void mma_rs64(float (&d)[NN], uint32_t a0, uint32_t a1, uint32_t a2, uint32_t a3, uint64_t db, int sd = 0){
  if constexpr (ACC == 1) asm volatile("wgmma.mma_async.sync.aligned.m64n64k16.f32.bf16.bf16 {%0,%1,%2,%3,%4,%5,%6,%7,%8,%9,%10,%11,%12,%13,%14,%15,%16,%17,%18,%19,%20,%21,%22,%23,%24,%25,%26,%27,%28,%29,%30,%31}, {%32,%33,%34,%35}, %36, 1, 1, 1, %37;"
   : "+f"(d[O+0]), "+f"(d[O+1]), "+f"(d[O+2]), "+f"(d[O+3]), "+f"(d[O+4]), "+f"(d[O+5]), "+f"(d[O+6]), "+f"(d[O+7]), "+f"(d[O+8]), "+f"(d[O+9]), "+f"(d[O+10]), "+f"(d[O+11]), "+f"(d[O+12]), "+f"(d[O+13]), "+f"(d[O+14]), "+f"(d[O+15]), "+f"(d[O+16]), "+f"(d[O+17]), "+f"(d[O+18]), "+f"(d[O+19]), "+f"(d[O+20]), "+f"(d[O+21]), "+f"(d[O+22]), "+f"(d[O+23]), "+f"(d[O+24]), "+f"(d[O+25]), "+f"(d[O+26]), "+f"(d[O+27]), "+f"(d[O+28]), "+f"(d[O+29]), "+f"(d[O+30]), "+f"(d[O+31])
   : "r"(a0), "r"(a1), "r"(a2), "r"(a3), "l"(db), "n"(TB));
  else if constexpr (ACC == 0) asm volatile("wgmma.mma_async.sync.aligned.m64n64k16.f32.bf16.bf16 {%0,%1,%2,%3,%4,%5,%6,%7,%8,%9,%10,%11,%12,%13,%14,%15,%16,%17,%18,%19,%20,%21,%22,%23,%24,%25,%26,%27,%28,%29,%30,%31}, {%32,%33,%34,%35}, %36, 0, 1, 1, %37;"
   : "=f"(d[O+0]), "=f"(d[O+1]), "=f"(d[O+2]), "=f"(d[O+3]), "=f"(d[O+4]), "=f"(d[O+5]), "=f"(d[O+6]), "=f"(d[O+7]), "=f"(d[O+8]), "=f"(d[O+9]), "=f"(d[O+10]), "=f"(d[O+11]), "=f"(d[O+12]), "=f"(d[O+13]), "=f"(d[O+14]), "=f"(d[O+15]), "=f"(d[O+16]), "=f"(d[O+17]), "=f"(d[O+18]), "=f"(d[O+19]), "=f"(d[O+20]), "=f"(d[O+21]), "=f"(d[O+22]), "=f"(d[O+23]), "=f"(d[O+24]), "=f"(d[O+25]), "=f"(d[O+26]), "=f"(d[O+27]), "=f"(d[O+28]), "=f"(d[O+29]), "=f"(d[O+30]), "=f"(d[O+31])
   : "r"(a0), "r"(a1), "r"(a2), "r"(a3), "l"(db), "n"(TB));
  else asm volatile("{\n.reg .pred p;\nsetp.ne.b32 p, %38, 0;\nwgmma.mma_async.sync.aligned.m64n64k16.f32.bf16.bf16 {%0,%1,%2,%3,%4,%5,%6,%7,%8,%9,%10,%11,%12,%13,%14,%15,%16,%17,%18,%19,%20,%21,%22,%23,%24,%25,%26,%27,%28,%29,%30,%31}, {%32,%33,%34,%35}, %36, p, 1, 1, %37;\n}"
   : "+f"(d[O+0]), "+f"(d[O+1]), "+f"(d[O+2]), "+f"(d[O+3]), "+f"(d[O+4]), "+f"(d[O+5]), "+f"(d[O+6]), "+f"(d[O+7]), "+f"(d[O+8]), "+f"(d[O+9]), "+f"(d[O+10]), "+f"(d[O+11]), "+f"(d[O+12]), "+f"(d[O+13]), "+f"(d[O+14]), "+f"(d[O+15]), "+f"(d[O+16]), "+f"(d[O+17]), "+f"(d[O+18]), "+f"(d[O+19]), "+f"(d[O+20]), "+f"(d[O+21]), "+f"(d[O+22]), "+f"(d[O+23]), "+f"(d[O+24]), "+f"(d[O+25]), "+f"(d[O+26]), "+f"(d[O+27]), "+f"(d[O+28]), "+f"(d[O+29]), "+f"(d[O+30]), "+f"(d[O+31])
   : "r"(a0), "r"(a1), "r"(a2), "r"(a3), "l"(db), "n"(TB), "r"(sd));
}
template<int O,int TB,int ACC,int NN> __device__ __forceinline__ void mma_ss128(float (&d)[NN], uint64_t da, uint64_t db, int sd = 0){
  if constexpr (ACC == 1) asm volatile("wgmma.mma_async.sync.aligned.m64n128k16.f32.bf16.bf16 {%0,%1,%2,%3,%4,%5,%6,%7,%8,%9,%10,%11,%12,%13,%14,%15,%16,%17,%18,%19,%20,%21,%22,%23,%24,%25,%26,%27,%28,%29,%30,%31,%32,%33,%34,%35,%36,%37,%38,%39,%40,%41,%42,%43,%44,%45,%46,%47,%48,%49,%50,%51,%52,%53,%54,%55,%56,%57,%58,%59,%60,%61,%62,%63}, %64, %65, 1, 1, 1, %67, %66;"
   : "+f"(d[O+0]), "+f"(d[O+1]), "+f"(d[O+2]), "+f"(d[O+3]), "+f"(d[O+4]), "+f"(d[O+5]), "+f"(d[O+6]), "+f"(d[O+7]), "+f"(d[O+8]), "+f"(d[O+9]), "+f"(d[O+10]), "+f"(d[O+11]), "+f"(d[O+12]), "+f"(d[O+13]), "+f"(d[O+14]), "+f"(d[O+15]), "+f"(d[O+16]), "+f"(d[O+17]), "+f"(d[O+18]), "+f"(d[O+19]), "+f"(d[O+20]), "+f"(d[O+21]), "+f"(d[O+22]), "+f"(d[O+23]), "+f"(d[O+24]), "+f"(d[O+25]), "+f"(d[O+26]), "+f"(d[O+27]), "+f"(d[O+28]), "+f"(d[O+29]), "+f"(d[O+30]), "+f"(d[O+31]), "+f"(d[O+32]), "+f"(d[O+33]), "+f"(d[O+34]), "+f"(d[O+35]), "+f"(d[O+36]), "+f"(d[O+37]), "+f"(d[O+38]), "+f"(d[O+39]), "+f"(d[O+40]), "+f"(d[O+41]), "+f"(d[O+42]), "+f"(d[O+43]), "+f"(d[O+44]), "+f"(d[O+45]), "+f"(d[O+46]), "+f"(d[O+47]), "+f"(d[O+48]), "+f"(d[O+49]), "+f"(d[O+50]), "+f"(d[O+51]), "+f"(d[O+52]), "+f"(d[O+53]), "+f"(d[O+54]), "+f"(d[O+55]), "+f"(d[O+56]), "+f"(d[O+57]), "+f"(d[O+58]), "+f"(d[O+59]), "+f"(d[O+60]), "+f"(d[O+61]), "+f"(d[O+62]), "+f"(d[O+63])
   : "l"(da), "l"(db), "n"(TB & 1), "n"(TB >> 1));
  else if constexpr (ACC == 0) asm volatile("wgmma.mma_async.sync.aligned.m64n128k16.f32.bf16.bf16 {%0,%1,%2,%3,%4,%5,%6,%7,%8,%9,%10,%11,%12,%13,%14,%15,%16,%17,%18,%19,%20,%21,%22,%23,%24,%25,%26,%27,%28,%29,%30,%31,%32,%33,%34,%35,%36,%37,%38,%39,%40,%41,%42,%43,%44,%45,%46,%47,%48,%49,%50,%51,%52,%53,%54,%55,%56,%57,%58,%59,%60,%61,%62,%63}, %64, %65, 0, 1, 1, %67, %66;"
   : "=f"(d[O+0]), "=f"(d[O+1]), "=f"(d[O+2]), "=f"(d[O+3]), "=f"(d[O+4]), "=f"(d[O+5]), "=f"(d[O+6]), "=f"(d[O+7]), "=f"(d[O+8]), "=f"(d[O+9]), "=f"(d[O+10]), "=f"(d[O+11]), "=f"(d[O+12]), "=f"(d[O+13]), "=f"(d[O+14]), "=f"(d[O+15]), "=f"(d[O+16]), "=f"(d[O+17]), "=f"(d[O+18]), "=f"(d[O+19]), "=f"(d[O+20]), "=f"(d[O+21]), "=f"(d[O+22]), "=f"(d[O+23]), "=f"(d[O+24]), "=f"(d[O+25]), "=f"(d[O+26]), "=f"(d[O+27]), "=f"(d[O+28]), "=f"(d[O+29]), "=f"(d[O+30]), "=f"(d[O+31]), "=f"(d[O+32]), "=f"(d[O+33]), "=f"(d[O+34]), "=f"(d[O+35]), "=f"(d[O+36]), "=f"(d[O+37]), "=f"(d[O+38]), "=f"(d[O+39]), "=f"(d[O+40]), "=f"(d[O+41]), "=f"(d[O+42]), "=f"(d[O+43]), "=f"(d[O+44]), "=f"(d[O+45]), "=f"(d[O+46]), "=f"(d[O+47]), "=f"(d[O+48]), "=f"(d[O+49]), "=f"(d[O+50]), "=f"(d[O+51]), "=f"(d[O+52]), "=f"(d[O+53]), "=f"(d[O+54]), "=f"(d[O+55]), "=f"(d[O+56]), "=f"(d[O+57]), "=f"(d[O+58]), "=f"(d[O+59]), "=f"(d[O+60]), "=f"(d[O+61]), "=f"(d[O+62]), "=f"(d[O+63])
   : "l"(da), "l"(db), "n"(TB & 1), "n"(TB >> 1));
  else asm volatile("{\n.reg .pred p;\nsetp.ne.b32 p, %68, 0;\nwgmma.mma_async.sync.aligned.m64n128k16.f32.bf16.bf16 {%0,%1,%2,%3,%4,%5,%6,%7,%8,%9,%10,%11,%12,%13,%14,%15,%16,%17,%18,%19,%20,%21,%22,%23,%24,%25,%26,%27,%28,%29,%30,%31,%32,%33,%34,%35,%36,%37,%38,%39,%40,%41,%42,%43,%44,%45,%46,%47,%48,%49,%50,%51,%52,%53,%54,%55,%56,%57,%58,%59,%60,%61,%62,%63}, %64, %65, p, 1, 1, %67, %66;\n}"
   : "+f"(d[O+0]), "+f"(d[O+1]), "+f"(d[O+2]), "+f"(d[O+3]), "+f"(d[O+4]), "+f"(d[O+5]), "+f"(d[O+6]), "+f"(d[O+7]), "+f"(d[O+8]), "+f"(d[O+9]), "+f"(d[O+10]), "+f"(d[O+11]), "+f"(d[O+12]), "+f"(d[O+13]), "+f"(d[O+14]), "+f"(d[O+15]), "+f"(d[O+16]), "+f"(d[O+17]), "+f"(d[O+18]), "+f"(d[O+19]), "+f"(d[O+20]), "+f"(d[O+21]), "+f"(d[O+22]), "+f"(d[O+23]), "+f"(d[O+24]), "+f"(d[O+25]), "+f"(d[O+26]), "+f"(d[O+27]), "+f"(d[O+28]), "+f"(d[O+29]), "+f"(d[O+30]), "+f"(d[O+31]), "+f"(d[O+32]), "+f"(d[O+33]), "+f"(d[O+34]), "+f"(d[O+35]), "+f"(d[O+36]), "+f"(d[O+37]), "+f"(d[O+38]), "+f"(d[O+39]), "+f"(d[O+40]), "+f"(d[O+41]), "+f"(d[O+42]), "+f"(d[O+43]), "+f"(d[O+44]), "+f"(d[O+45]), "+f"(d[O+46]), "+f"(d[O+47]), "+f"(d[O+48]), "+f"(d[O+49]), "+f"(d[O+50]), "+f"(d[O+51]), "+f"(d[O+52]), "+f"(d[O+53]), "+f"(d[O+54]), "+f"(d[O+55]), "+f"(d[O+56]), "+f"(d[O+57]), "+f"(d[O+58]), "+f"(d[O+59]), "+f"(d[O+60]), "+f"(d[O+61]), "+f"(d[O+62]), "+f"(d[O+63])
   : "l"(da), "l"(db), "n"(TB & 1), "n"(TB >> 1), "r"(sd));
}
template<int O,int TB,int ACC,int NN> __device__ __forceinline__ void mma_rs128(float (&d)[NN], uint32_t a0, uint32_t a1, uint32_t a2, uint32_t a3, uint64_t db, int sd = 0){
  if constexpr (ACC == 1) asm volatile("wgmma.mma_async.sync.aligned.m64n128k16.f32.bf16.bf16 {%0,%1,%2,%3,%4,%5,%6,%7,%8,%9,%10,%11,%12,%13,%14,%15,%16,%17,%18,%19,%20,%21,%22,%23,%24,%25,%26,%27,%28,%29,%30,%31,%32,%33,%34,%35,%36,%37,%38,%39,%40,%41,%42,%43,%44,%45,%46,%47,%48,%49,%50,%51,%52,%53,%54,%55,%56,%57,%58,%59,%60,%61,%62,%63}, {%64,%65,%66,%67}, %68, 1, 1, 1, %69;"
   : "+f"(d[O+0]), "+f"(d[O+1]), "+f"(d[O+2]), "+f"(d[O+3]), "+f"(d[O+4]), "+f"(d[O+5]), "+f"(d[O+6]), "+f"(d[O+7]), "+f"(d[O+8]), "+f"(d[O+9]), "+f"(d[O+10]), "+f"(d[O+11]), "+f"(d[O+12]), "+f"(d[O+13]), "+f"(d[O+14]), "+f"(d[O+15]), "+f"(d[O+16]), "+f"(d[O+17]), "+f"(d[O+18]), "+f"(d[O+19]), "+f"(d[O+20]), "+f"(d[O+21]), "+f"(d[O+22]), "+f"(d[O+23]), "+f"(d[O+24]), "+f"(d[O+25]), "+f"(d[O+26]), "+f"(d[O+27]), "+f"(d[O+28]), "+f"(d[O+29]), "+f"(d[O+30]), "+f"(d[O+31]), "+f"(d[O+32]), "+f"(d[O+33]), "+f"(d[O+34]), "+f"(d[O+35]), "+f"(d[O+36]), "+f"(d[O+37]), "+f"(d[O+38]), "+f"(d[O+39]), "+f"(d[O+40]), "+f"(d[O+41]), "+f"(d[O+42]), "+f"(d[O+43]), "+f"(d[O+44]), "+f"(d[O+45]), "+f"(d[O+46]), "+f"(d[O+47]), "+f"(d[O+48]), "+f"(d[O+49]), "+f"(d[O+50]), "+f"(d[O+51]), "+f"(d[O+52]), "+f"(d[O+53]), "+f"(d[O+54]), "+f"(d[O+55]), "+f"(d[O+56]), "+f"(d[O+57]), "+f"(d[O+58]), "+f"(d[O+59]), "+f"(d[O+60]), "+f"(d[O+61]), "+f"(d[O+62]), "+f"(d[O+63])
   : "r"(a0), "r"(a1), "r"(a2), "r"(a3), "l"(db), "n"(TB));
  else if constexpr (ACC == 0) asm volatile("wgmma.mma_async.sync.aligned.m64n128k16.f32.bf16.bf16 {%0,%1,%2,%3,%4,%5,%6,%7,%8,%9,%10,%11,%12,%13,%14,%15,%16,%17,%18,%19,%20,%21,%22,%23,%24,%25,%26,%27,%28,%29,%30,%31,%32,%33,%34,%35,%36,%37,%38,%39,%40,%41,%42,%43,%44,%45,%46,%47,%48,%49,%50,%51,%52,%53,%54,%55,%56,%57,%58,%59,%60,%61,%62,%63}, {%64,%65,%66,%67}, %68, 0, 1, 1, %69;"
   : "=f"(d[O+0]), "=f"(d[O+1]), "=f"(d[O+2]), "=f"(d[O+3]), "=f"(d[O+4]), "=f"(d[O+5]), "=f"(d[O+6]), "=f"(d[O+7]), "=f"(d[O+8]), "=f"(d[O+9]), "=f"(d[O+10]), "=f"(d[O+11]), "=f"(d[O+12]), "=f"(d[O+13]), "=f"(d[O+14]), "=f"(d[O+15]), "=f"(d[O+16]), "=f"(d[O+17]), "=f"(d[O+18]), "=f"(d[O+19]), "=f"(d[O+20]), "=f"(d[O+21]), "=f"(d[O+22]), "=f"(d[O+23]), "=f"(d[O+24]), "=f"(d[O+25]), "=f"(d[O+26]), "=f"(d[O+27]), "=f"(d[O+28]), "=f"(d[O+29]), "=f"(d[O+30]), "=f"(d[O+31]), "=f"(d[O+32]), "=f"(d[O+33]), "=f"(d[O+34]), "=f"(d[O+35]), "=f"(d[O+36]), "=f"(d[O+37]), "=f"(d[O+38]), "=f"(d[O+39]), "=f"(d[O+40]), "=f"(d[O+41]), "=f"(d[O+42]), "=f"(d[O+43]), "=f"(d[O+44]), "=f"(d[O+45]), "=f"(d[O+46]), "=f"(d[O+47]), "=f"(d[O+48]), "=f"(d[O+49]), "=f"(d[O+50]), "=f"(d[O+51]), "=f"(d[O+52]), "=f"(d[O+53]), "=f"(d[O+54]), "=f"(d[O+55]), "=f"(d[O+56]), "=f"(d[O+57]), "=f"(d[O+58]), "=f"(d[O+59]), "=f"(d[O+60]), "=f"(d[O+61]), "=f"(d[O+62]), "=f"(d[O+63])
   : "r"(a0), "r"(a1), "r"(a2), "r"(a3), "l"(db), "n"(TB));
  else asm volatile("{\n.reg .pred p;\nsetp.ne.b32 p, %70, 0;\nwgmma.mma_async.sync.aligned.m64n128k16.f32.bf16.bf16 {%0,%1,%2,%3,%4,%5,%6,%7,%8,%9,%10,%11,%12,%13,%14,%15,%16,%17,%18,%19,%20,%21,%22,%23,%24,%25,%26,%27,%28,%29,%30,%31,%32,%33,%34,%35,%36,%37,%38,%39,%40,%41,%42,%43,%44,%45,%46,%47,%48,%49,%50,%51,%52,%53,%54,%55,%56,%57,%58,%59,%60,%61,%62,%63}, {%64,%65,%66,%67}, %68, p, 1, 1, %69;\n}"
   : "+f"(d[O+0]), "+f"(d[O+1]), "+f"(d[O+2]), "+f"(d[O+3]), "+f"(d[O+4]), "+f"(d[O+5]), "+f"(d[O+6]), "+f"(d[O+7]), "+f"(d[O+8]), "+f"(d[O+9]), "+f"(d[O+10]), "+f"(d[O+11]), "+f"(d[O+12]), "+f"(d[O+13]), "+f"(d[O+14]), "+f"(d[O+15]), "+f"(d[O+16]), "+f"(d[O+17]), "+f"(d[O+18]), "+f"(d[O+19]), "+f"(d[O+20]), "+f"(d[O+21]), "+f"(d[O+22]), "+f"(d[O+23]), "+f"(d[O+24]), "+f"(d[O+25]), "+f"(d[O+26]), "+f"(d[O+27]), "+f"(d[O+28]), "+f"(d[O+29]), "+f"(d[O+30]), "+f"(d[O+31]), "+f"(d[O+32]), "+f"(d[O+33]), "+f"(d[O+34]), "+f"(d[O+35]), "+f"(d[O+36]), "+f"(d[O+37]), "+f"(d[O+38]), "+f"(d[O+39]), "+f"(d[O+40]), "+f"(d[O+41]), "+f"(d[O+42]), "+f"(d[O+43]), "+f"(d[O+44]), "+f"(d[O+45]), "+f"(d[O+46]), "+f"(d[O+47]), "+f"(d[O+48]), "+f"(d[O+49]), "+f"(d[O+50]), "+f"(d[O+51]), "+f"(d[O+52]), "+f"(d[O+53]), "+f"(d[O+54]), "+f"(d[O+55]), "+f"(d[O+56]), "+f"(d[O+57]), "+f"(d[O+58]), "+f"(d[O+59]), "+f"(d[O+60]), "+f"(d[O+61]), "+f"(d[O+62]), "+f"(d[O+63])
   : "r"(a0), "r"(a1), "r"(a2), "r"(a3), "l"(db), "n"(TB), "r"(sd));
}

#define NEARLY 0
#define XAHEAD 3
#define HEADN 6
#define WBATCH 1
#define NOLDS 2
#define NOSEND 0
#define MSPLIT 3
#define SPACE 0
#define WPF 1
#define WAFTER 7
#define WPACE 0
#define GATE_AT 4
#define TPACE 40
#define PFMODE 0
#define MAPMODE 1
template <int V> struct IC { static constexpr int value = V; };
struct Maps { CUtensorMap x, ft, g64, u64, e, wr, wi, xs, ts, t, g32, u32, d224, o; };

constexpr int NCTA = 130;
constexpr int U = 16384;
constexpr int TB = 36864;
constexpr int OFF_RING = 8 * U, OFF_Z = 9 * U, OFF_XB = 12 * U, OFF_T = 13 * U, OFF_D = OFF_T;
constexpr int OFF_BAR = 14 * U, OFF_SP = OFF_BAR + 512, OFF_G = OFF_SP + 1024 + 128;
constexpr int SMEM_BYTES = OFF_G + 512;
constexpr int B_FX = 0, B_FA = 8, B_FT = 12, B_Z = 16, B_W = 24, B_HX = 25, B_TL = 26, B_HP = 27, B_WR = 30, B_E0 = 34;
constexpr int B_EA = 35, B_ET = 39, B_PZ = 43, B_RDY = 45, B_FE = 46;
constexpr int B_T = 50, B_XS = 51, B_G = 53, NBAR = 54;
__host__ __device__ constexpr int rslot(int n) { return n & 3; }
__host__ __device__ constexpr int rpar(int n) { return (n >> 2) & 1; }

__global__ void __cluster_dims__(2, 1, 1) __launch_bounds__(512, 1)
fused_kernel(Work* __restrict__ ws, const uint16_t* __restrict__ dtab, const __nv_bfloat16* __restrict__ w_r, const __nv_bfloat16* __restrict__ w_i,
             const __nv_bfloat16* __restrict__ gate_w, const __grid_constant__ Maps maps) {
  extern __shared__ __align__(1024) uint8_t smem[];
  const uint32_t sb = smem_u32(smem);
  const uint32_t bars = sb + OFF_BAR;
  const int tid = threadIdx.x, lane = tid & 31;
  const int warp = __shfl_sync(0xffffffffu, tid >> 5, 0);
  const bool helper = blockIdx.x >= 128;
  const int cl = (blockIdx.x >> 1) & 63, rank = blockIdx.x & 1;
  const int q4 = (cl & 1) | ((cl >> 2) & 2), rb = ((cl >> 1) & 3) | ((cl >> 4) << 2);
  const int j = 2 * q4 + rank;
  const int f_full = 448 * q4 + (rank ? 256 : 0);
  const int f_half = 448 * q4 + (rank ? 224 : 192);
  const int kg = 2 * j + (rb >> 3), tn = rb & 7;

  if (tid == 64) { PROF_EV(0); PROF_CK(40); }
  if (warp < 8) {
    asm volatile("barrier.cluster.arrive.relaxed.aligned;" ::: "memory");
    asm volatile("setmaxnreg.inc.sync.aligned.u32 192;");
    if (!helper) {
      const int wg = warp >> 2, w = warp & 3, g = lane >> 2;
      const bool elect = (tid & 127) == 0;
      float cX[32], cA[64], cB[64], cC[64], ci[64], ct[64];
      const int zero = blockIdx.x >> 16;
      uint32_t h[56], yf[16];
      const uint32_t d0 = (sb & 0x3FFFF) >> 4;
      const uint32_t dK = d0 | (1u << 16), dN = d0 | (512u << 16);
      const uint32_t dX = dK + wg * 512;
      constexpr uint32_t RING = OFF_RING >> 4;
      auto waitA = [&](int n) { mbar_wait(bars + 8 * (B_FA + rslot(n)), rpar(n)); };
      auto freeA = [&](int n) { mbar_arrive_if(elect, bars + 8 * (B_EA + rslot(n))); };
      auto nop = [] {};

      asm volatile("bar.sync 0, 384;" ::: "memory");
#pragma unroll 1
      for (int i = 0; i < 4; i++) {
        const uint64_t dx = d128(dX + i * 2048), df = d128(dK + (OFF_XB >> 4) + (i & 1) * 1024);
        mbar_wait(bars + 8 * (B_FX + 2 * i), 0);
        wg_fence();
        mma_ss64<0, 0, 2>(cX, df, dx, i);
        mma_ss64<0, 0, 1>(cX, df + 2, dx + 2);
        wg_commit(); wg_wait<1>();
        mbar_arrive_if(elect && i, bars + 8 * (B_EA + rslot(i - 1)));
        mma_ss64<0, 0, 1>(cX, df + 4, dx + 4);
        mma_ss64<0, 0, 1>(cX, df + 6, dx + 6);
        if (i == 0 && tid == 0) PROF_EV(1);
        mbar_wait(bars + 8 * (B_FX + 2 * i + 1), 0);
        wg_fence();
#pragma unroll
        for (int k = 0; k < 4; k++) mma_ss64<0, 0, 1>(cX, df + (512 + k * 2), dx + (1024 + k * 2));
        wg_commit();
        waitA(i);
        wg_fence();
        const uint64_t da = d128(dX + i * 1024), db = d128(dN + RING + i * 1024);
        mma_ss128<0, 1, 2>(cA, da, db, i);
        wg_commit(); wg_wait<1>();
        mbar_arrive_if(elect, bars + 8 * (B_FE + i));
#pragma unroll
        for (int k = 1; k < 4; k++) mma_ss128<0, 1, 1>(cA, da + k * 2, db + k * 128);
        wg_commit();
      }
      fence_regs<0, 32>(cX);
#pragma unroll
      for (int e = 0; e < 16; e++) yf[e] = pack_pin(cX[2 * e], cX[2 * e + 1]);
      if (tid == 0) PROF_EV(2);
      {
        waitA(4); mbar_wait(bars + 8 * B_E0, 0);
        const uint64_t de = d128(dN + (wg ? RING : OFF_XB >> 4));
        wg_fence();
        mma_rs128<0, 1, 0>(cB, yf[0], yf[1], yf[2], yf[3], de);
        wg_commit();
        wg_wait<1>();
        freeA(3);
#pragma unroll
        for (int k = 1; k < 4; k++) mma_rs128<0, 1, 1>(cB, yf[4 * k], yf[4 * k + 1], yf[4 * k + 2], yf[4 * k + 3], de + k * 128);
        wg_commit();
      }
      bool rel = false;
      auto acquire = [&](int n) {
        rel = elect;
        if (!mbar_try(bars + 8 * (B_FA + rslot(n)), rpar(n))) { wg_wait<0>(); freeA(n - 1); rel = false; waitA(n); }
      };
      auto freeP = [&](int n) { mbar_arrive_if(rel, bars + 8 * (B_EA + rslot(n - 1))); };
      auto ffn_step = [&](auto first, auto split, float (&acc)[64], int n, int kb, auto done, auto work) {
        constexpr int SPLIT = decltype(split)::value;
        acquire(n);
        wg_fence();
        const uint64_t dx = d128(dX + kb * 1024), db = d128(dN + RING + rslot(n) * 1024);
        mma_ss128<0, 1, decltype(first)::value>(acc, dx, db, kb);
#pragma unroll
        for (int k = 1; k < SPLIT; k++) mma_ss128<0, 1, 1>(acc, dx + k * 2, db + k * 128);
        wg_commit();
        work();
        wg_wait<1>();
        freeP(n);
        done();
        if (SPLIT < 4) {
          wg_fence();
#pragma unroll
          for (int k = SPLIT; k < 4; k++) mma_ss128<0, 1, 1>(acc, dx + k * 2, db + k * 128);
          wg_commit();
        }
      };
      {
        const int s0 = 2 * rb + wg, kr = 2 * ((s0 & 1) | ((s0 & 4) >> 1));
        const int m = lane >> 3, r = lane & 7;
        const uint32_t a0 = sb + OFF_XB + wg * 8192 + (((w >> 1) * 8 + (m >> 1)) * 2 + (w & 1)) * 256 + (m & 1) * 128 + ((r ^ (kr + (m & 1))) << 4);
        ffn_step(IC<1>(), IC<4>(), cA, 5, 4, [&] { fence_regs<0, 64>(cB); }, nop);
        asm volatile("bar.sync 5, 256;" ::: "memory");
#pragma unroll
        for (int i = 0; i < 4; i++)
          stsm4t(a0 + i * 1024, pack_bf16(cB[8 * i] - cB[34 + 8 * i], cB[8 * i + 1] - cB[35 + 8 * i]),
                 pack_bf16(cB[32 + 8 * i] + cB[8 * i + 2], cB[33 + 8 * i] + cB[8 * i + 3]),
                 pack_bf16(cB[8 * i + 4] - cB[38 + 8 * i], cB[8 * i + 5] - cB[39 + 8 * i]),
                 pack_bf16(cB[36 + 8 * i] + cB[8 * i + 6], cB[37 + 8 * i] + cB[8 * i + 7]));
        if (j == 0 && w == 0) {
          const uint32_t a1 = r ? sb + OFF_SP + 1024 : sb + OFF_SP + wg * 512 + (m & 1) * 256 + (m >> 1) * 128;
#pragma unroll
          for (int n = 0; n < 8; n++)
            asm volatile("stmatrix.sync.aligned.m8n8.x4.shared.b16 [%0], {%1,%2,%3,%4};" ::"r"(a1 + ((n ^ (kr + (m >> 1))) << 4)),
                         "r"(pack_bf16(cB[4 * n], cB[4 * n + 1])), "r"(pack_bf16(cB[4 * n + 2], cB[4 * n + 3])),
                         "r"(pack_bf16(cB[32 + 4 * n], cB[33 + 4 * n])), "r"(pack_bf16(cB[34 + 4 * n], cB[35 + 4 * n])) : "memory");
        }
        ffn_step(IC<1>(), IC<2>(), cA, 6, 5, nop, [&] {
          asm volatile("fence.proxy.async.shared::cta;" ::: "memory");
          __syncwarp();
          mbar_arrive_if(lane == 0, bars + 8 * (B_XS + wg));
          if (tid == 0) PROF_EV(3);
        });
      }
#pragma unroll 1
      for (int kb = 6; kb < 8; kb++) ffn_step(IC<1>(), IC<1>(), cA, 1 + kb, kb, nop, nop);
      float g0 = 0.f, g1 = 0.f;
      uint32_t tag = 0;
      auto glu = [&](auto& acc, int half, int ho, int i0, int i1) {
#pragma unroll
        for (int i = i0; i < i1; i++) {
          const float o = 1.0f - ((i & 1) ? g1 : g0);
          asm volatile("" : "+f"(acc[2 * i]), "+f"(acc[2 * i + 1]), "+f"(acc[half + 2 * i]), "+f"(acc[half + 1 + 2 * i])::"memory");
          h[ho + i] = pack_pin(fmaxf(acc[2 * i], 0.f) * acc[half + 2 * i] * o, fmaxf(acc[2 * i + 1], 0.f) * acc[half + 1 + 2 * i] * o);
        }
      };
      ffn_step(IC<2>(), IC<1>(), cB, 9, zero, nop, nop);
#pragma unroll 1
      for (int kb = 1; kb < 8; kb++)
        ffn_step(IC<1>(), IC<1>(), cB, 9 + kb, kb, nop, [&] {
          if (kb == 4 + wg) {
            mbar_wait(bars + 8 * B_G, 0);
            const uint32_t gb0 = *(const uint32_t*)(smem + OFF_G + (wg * 64 + w * 16 + g) * 4), gb1 = *(const uint32_t*)(smem + OFF_G + (wg * 64 + w * 16 + g + 8) * 4);
            tag = gb0 & 1; g0 = __uint_as_float(gb0 & ~1u); g1 = __uint_as_float(gb1 & ~1u);
            glu(cA, 32, 0, 0, 8);
          } else if (kb == 6 + wg) glu(cA, 32, 0, 8, 16);
        });
      if (tid == 0) PROF_EV(4);
      ffn_step(IC<0>(), IC<1>(), cC, 17, 0, nop, nop);
#pragma unroll 1
      for (int kb = 1; kb < 8; kb++)
        ffn_step(IC<1>(), IC<1>(), cC, 17 + kb, kb, nop, [&] {
          if (kb == 1 + wg) glu(cB, 32, 16, 0, 8);
          else if (kb == 3 + wg) glu(cB, 32, 16, 8, 16);
        });
      if (tid == 0) PROF_EV(5);
      auto m_step = [&](auto first, int i) {
        acquire(25 + i);
        wg_fence();
        const uint64_t dx = d128(dX + i * 2048), dm = d64(dN + RING + rslot(25 + i) * 1024);
        mma_ss64<0, 1, decltype(first)::value>(ct, dx, dm);
#pragma unroll
        for (int k = 1; k < MSPLIT; k++) mma_ss64<0, 1, 1>(ct, dx + ((k >> 2) * 1024 + (k & 3) * 2), dm + k * 64);
        wg_commit();
        wg_wait<1>();
        mbar_arrive_if(rel && i < 3, bars + 8 * (B_EA + rslot(24 + i)));
        mbar_arrive_if(elect && i, bars + 8 * (B_ET + i - 1));
        wg_fence();
#pragma unroll
        for (int k = MSPLIT; k < 8; k++) mma_ss64<0, 1, 1>(ct, dx + ((k >> 2) * 1024 + (k & 3) * 2), dm + k * 64);
        wg_commit();
      };
      auto freeT = [&](int t) { mbar_arrive_if(elect, bars + 8 * (B_ET + t)); };
      m_step(IC<0>(), 0);
#pragma unroll 1
      for (int i = 1; i < 5; i++) {
        if (i == 1 + wg) glu(cC, 32, 32, 0, 8);
        else if (i == 3 + wg) glu(cC, 32, 32, 8, 16);
        if (i < 4) m_step(IC<1>(), i);
      }
      waitA(29 + wg);
      if (tid == 0) PROF_EV(6);
      if (tid == 128) PROF_EV(27);
      mbar_wait(bars + 8 * (j == 0 ? B_T : B_TL), 0);
      if (tid == 0) PROF_EV(7);
      wg_fence();
      {
        const uint64_t dt = d128(dN + (OFF_T >> 4) + wg * 512), de = d128(dK + RING + (1 + wg) * 1024);
        mma_ss64<0, 1, 0>(ci, de, dt);
        mma_ss64<32, 1, 0>(ci, de + 512, dt);
#pragma unroll
        for (int k = 1; k < 4; k++) {
          mma_ss64<0, 1, 1>(ci, de + k * 2, dt + k * 128);
          mma_ss64<32, 1, 1>(ci, de + (512 + k * 2), dt + k * 128);
        }
        wg_commit();
        wg_wait<1>();
        freeT(3);
        fence_regs<0, 32>(ct);
        glu(ct, 16, 48, 0, 8);
      }

      auto twait = [&](uint32_t bar, uint32_t par, int) { mbar_wait(bar, par); };
      auto fetch = [&](uint4 (&pv)[4], int z) {
        twait(bars + 8 * (z < 4 ? B_Z + 2 * z + wg : B_HP + z - 4), 0, 8 + z);
        const uint8_t* src = smem + (z < 4 ? OFF_Z + z * U : (z - 4) * U) + tid * 16;
#pragma unroll
        for (int i = 0; i < 4; i++) pv[i] = *(const uint4*)(src + i * 4096);
      };
      auto check = [&](uint4 (&pv)[4], int z) {
        const uint32_t t0 = (uint32_t)clock();
        while (__any_sync(0xffffffffu, ((pv[0].x ^ tag) | (pv[1].x ^ tag) | (pv[2].x ^ tag) | (pv[3].x ^ tag)) & 1)) {
#pragma unroll
          for (int i = 0; i < 4; i++) pv[i] = ld_x4(ws->part + (size_t)((rb * 8 + j) * 3 + z - 4) * 1024 + tid + i * 256);
          spin_guard(t0);
        }
#pragma unroll
        for (int i = 0; i < 4; i++) pv[i].x &= ~1u;
      };
      auto head = [&](auto off, int t, bool init) {
        constexpr int O = decltype(off)::value;
        twait(bars + 8 * (B_FT + (t & 3)), t >> 2, t);
        const uint64_t db = d128(dN + (t & 3) * (TB >> 4) + rank * 256);
        wg_fence();
        mma_rs64<O, 1, 2>(ct, h[0], h[1], h[2], h[3], db, zero + init);
#pragma unroll
        for (int k = 1; k < 6; k++) mma_rs64<O, 1, 1>(ct, h[4 * k], h[4 * k + 1], h[4 * k + 2], h[4 * k + 3], db + k * 128);
        wg_commit();
        wg_wait<1>();
      };
      auto rest = [&](auto off, int t, int z) {
        constexpr int O = decltype(off)::value, P = 32 - O;
        const uint64_t db = d128(dN + (t & 3) * (TB >> 4)), dw = db + rank * 256, dm = db + (rank ? 0 : 1536);
        wg_fence();
#pragma unroll
        for (int k = 6; k < 12; k++) mma_rs64<O, 1, 1>(ct, h[4 * k], h[4 * k + 1], h[4 * k + 2], h[4 * k + 3], dw + k * 128);
        wg_commit();
        uint4 pv[4];
        if (z >= 0) fetch(pv, z);
        wg_fence();
#pragma unroll
        for (int k = 0; k < 2; k++) mma_rs64<O, 1, 1>(ct, h[48 + 4 * k], h[49 + 4 * k], h[50 + 4 * k], h[51 + 4 * k], dm + k * 128);
#pragma unroll
        for (int k = 0; k < 4; k++) mma_rs64<O, 1, 1>(ct, yf[4 * k], yf[4 * k + 1], yf[4 * k + 2], yf[4 * k + 3], db + (14 + k) * 128);
        wg_commit();
        if (z >= 0) {
          if (z >= 4) check(pv, z);
#pragma unroll
          for (int i = 0; i < 4; i++) {
            const uint32_t a[4] = {pv[i].x, pv[i].y, pv[i].z, pv[i].w};
#pragma unroll
            for (int e = 0; e < 4; e++) { ct[P + 8 * i + 2 * e] = bf_lo(a[e]); ct[P + 8 * i + 2 * e + 1] = bf_hi(a[e]); }
          }
        }
      };
      const uint32_t peerZ = mapa(sb + OFF_Z + tid * 16, rank ^ 1), peerB = mapa(bars + 8 * (B_Z + wg), rank ^ 1);
      auto send = [&](auto off, int t) {
        constexpr int O = decltype(off)::value;
        fence_regs<O, 32>(ct);
        const bool grid = t >= 3 && t < 6;
        const int z = grid ? t - 3 : t == 6 ? 3 : t;
        uint32_t pk[16];
#pragma unroll
        for (int i = 0; i < 16; i++) pk[i] = pack_bf16(ct[O + 2 * i], ct[O + 2 * i + 1]);
        if (grid) {
          const int owner = rb * 8 + 2 * ((q4 + z + 1) & 3) + rank;
          uint4* dst = ws->part + (size_t)(owner * 3 + z) * 1024 + tid;
#pragma unroll
          for (int i = 0; i < 4; i++) st_x4(dst + i * 256, (pk[4 * i] & ~1u) | tag, pk[4 * i + 1], pk[4 * i + 2], pk[4 * i + 3]);
          __syncwarp();
          hint_add_if(lane == 0, &ws->cntP[32 * owner + z]);
        } else {
#pragma unroll
          for (int i = 0; i < 4; i++)
            asm volatile("st.async.weak.shared::cluster.mbarrier::complete_tx::bytes.v4.b32 [%0], {%1,%2,%3,%4}, [%5];" ::"r"(peerZ + z * U + i * 4096),
                         "r"(pk[4 * i]), "r"(pk[4 * i + 1]), "r"(pk[4 * i + 2]), "r"(pk[4 * i + 3]), "r"(peerB + 16 * z) : "memory");
        }
      };
      asm volatile("barrier.cluster.wait.aligned;" ::: "memory");
      head(IC<0>(), 0, false);
      if (elect) asm volatile("mbarrier.arrive.shared::cluster.b64 _, [%0];" ::"r"(mapa(bars + 8 * B_RDY, rank ^ 1)) : "memory");
      fence_regs<0, 64>(ci);
#pragma unroll
      for (int i = 0; i < 16; i++) {
        const float gg = ((i & 1) ? g1 : g0) * (2.0f / (2048.0f * 512.0f));
        if (i & 2) yf[i] = pack_pin((ci[2 * i] - ci[28 + 2 * i]) * gg, (ci[2 * i + 1] - ci[29 + 2 * i]) * gg);
        else yf[i] = pack_pin((ci[2 * i] + ci[36 + 2 * i]) * gg, (ci[2 * i + 1] + ci[37 + 2 * i]) * gg);
      }
      if (tid == 0) PROF_EV(8);
      if (tid == 128) PROF_EV(28);
#pragma unroll 1
      for (int t = 0;; t += 2) {
        rest(IC<0>(), t, t - 2);
        head(IC<32>(), t + 1, t >= 2);
        mbar_arrive_if(elect && t < 6, bars + 8 * (B_ET + t));
        if (t == 0) twait(bars + 8 * B_RDY, 0, 15);
        send(IC<0>(), t);
        rest(IC<32>(), t + 1, (t & 2) ? t - 1 : -1);
        if (t == 6) break;
        head(IC<0>(), t + 2, t == 2);
        mbar_arrive_if(elect, bars + 8 * (B_ET + t + 1));
        send(IC<32>(), t + 1);
      }
      if (tid == 0) PROF_EV(9);
      if (tid == 128) PROF_EV(29);
      {
        float (&sum)[64] = ct;
        uint4 p2[4], p3[4];
        fetch(p3, 3);
        if (tid == 0) PROF_EV(25);
        fetch(p2, 6);
        if (tid == 0) PROF_EV(24);
        check(p2, 6);
#pragma unroll
        for (int i = 0; i < 4; i++) {
          const uint32_t b[4] = {p2[i].x, p2[i].y, p2[i].z, p2[i].w}, c[4] = {p3[i].x, p3[i].y, p3[i].z, p3[i].w};
#pragma unroll
          for (int e = 0; e < 4; e++) {
            sum[8 * i + 2 * e] += bf_lo(c[e]) + bf_lo(b[e]);
            sum[8 * i + 2 * e + 1] += bf_hi(c[e]) + bf_hi(b[e]);
          }
        }
        if (tid == 0) PROF_EV(14);
        wg_wait<0>();
        fence_regs<32, 32>(ct);
#pragma unroll
        for (int i = 0; i < 32; i++) sum[i] += ct[32 + i];
        const uint32_t stg = sb + OFF_T + warp * 2048;
        const int mr = (lane & 7) + ((lane >> 3) & 1) * 8, mc = lane >> 4;
#pragma unroll
        for (int i = 0; i < 4; i++) {
          const uint32_t a = stg + mr * 128 + (((2 * i + mc) ^ (mr & 7)) << 4);
          asm volatile("stmatrix.sync.aligned.m8n8.x4.shared.b16 [%0], {%1,%2,%3,%4};" ::"r"(a), "r"(pack_bf16(sum[8 * i], sum[8 * i + 1])),
                       "r"(pack_bf16(sum[8 * i + 2], sum[8 * i + 3])), "r"(pack_bf16(sum[8 * i + 4], sum[8 * i + 5])),
                       "r"(pack_bf16(sum[8 * i + 6], sum[8 * i + 7])) : "memory");
        }
        asm volatile("fence.proxy.async.shared::cta;" ::: "memory");
        __syncwarp();
        if (elect_one()) {
          asm volatile("cp.async.bulk.tensor.3d.global.shared::cta.bulk_group [%0, {%2, %3, %4}], [%1];" ::"l"(&maps.o), "r"(stg), "r"(64 * j),
                       "r"(16 * w), "r"(2 * rb + wg) : "memory");
          asm volatile("cp.async.bulk.commit_group;\ncp.async.bulk.wait_group.read 0;" ::: "memory");
        }
      }
      if (tid == 0) { PROF_EV(15); PROF_CK(41); }
      if (tid == 128) PROF_EV(30);
    }
  } else if (warp < 12) {
    asm volatile("setmaxnreg.dec.sync.aligned.u32 104;");
    asm volatile("barrier.cluster.arrive.relaxed.aligned;" ::: "memory");
    const int t = tid - 256, w = warp - 8;
    const uint32_t ep = ld_x1(&ws->epoch[blockIdx.x * 8]);
    const uint32_t tag = (ep + 1) & 1;
    auto w_issue = [&](const CUtensorMap* m) {
          if (elect_one()) { mbar_expect_tx(bars + 8 * (B_WR + w), 3072); tma4d(sb + OFF_T + w * 3072, m, bars + 8 * (B_WR + w), 16 * kg, 0, 2 * w, tn); }
          __syncwarp();
    };
    auto gate_rows = [&] {
      const int r = 16 * j + 4 * w + (lane >> 3);
      const uint4* pg = (const uint4*)gate_w + (lane & 7);
      {
        float a = 0.f;
        asm volatile("bar.sync 4, 256;" ::: "memory");
#pragma unroll 1
        for (int hf = 0; hf < 2; hf++) {
          uint4 v[4], u[4];
#pragma unroll
          for (int kb = 0; kb < 4; kb++) v[kb] = __ldg(pg + (4 * hf + kb) * 8);
          mbar_wait(bars + 8 * (B_FE + 1 + 2 * hf), 0);
          if (hf) w_issue(&maps.wr);
#pragma unroll
          for (int kb = 0; kb < 4; kb++) u[kb] = *(const uint4*)(smem + (4 * hf + kb) * U + r * 128 + (((lane ^ r) & 7) << 4));
#pragma unroll
          for (int kb = 0; kb < 4; kb++) {
            a = fmaf(bf_lo(u[kb].x), bf_lo(v[kb].x), a); a = fmaf(bf_hi(u[kb].x), bf_hi(v[kb].x), a);
            a = fmaf(bf_lo(u[kb].y), bf_lo(v[kb].y), a); a = fmaf(bf_hi(u[kb].y), bf_hi(v[kb].y), a);
            a = fmaf(bf_lo(u[kb].z), bf_lo(v[kb].z), a); a = fmaf(bf_hi(u[kb].z), bf_hi(v[kb].z), a);
            a = fmaf(bf_lo(u[kb].w), bf_lo(v[kb].w), a); a = fmaf(bf_hi(u[kb].w), bf_hi(v[kb].w), a);
          }
        }
#pragma unroll
        for (int o = 4; o; o >>= 1) a += __shfl_xor_sync(0xffffffffu, a, o);
        if ((lane & 7) == 0)
          asm volatile("st.relaxed.gpu.global.f32 [%0], %1;" ::"l"(ws->gate + rb * 128 + r), "f"(tagf(__fdividef(1.0f, 1.0f + __expf(-a)), tag)) : "memory");
        if (t == 0) PROF_EV(18);
      }
    };
    {
      const int g = lane >> 2, q = lane & 3;
      uint32_t wf[32];
      if (!helper) {
        gate_rows();
        const uint32_t wa = sb + OFF_T + w * (3072 + 4) + q * 48 + g * 2;
#pragma unroll 1
        for (int ri = 0; ri < 2; ri++) {
          mbar_wait(bars + 8 * (B_WR + w), ri);
#pragma unroll
          for (int n2 = 0; n2 < NOLDS; n2++) {
            uint32_t v[16];
#pragma unroll
            for (int i = 0; i < 16; i++)
              asm volatile("ld.shared.u16 %0, [%1];" : "=r"(v[i]) : "r"(wa + (4 * n2 + ((i >> 1) & 3)) * 192 + (i & 1) * (1536 + 2) + (i >> 3) * 16) : "memory");
#pragma unroll
            for (int i = 0; i < 16; i++) {
              uint32_t& d = wf[(i >> 3) * 16 + 8 * n2 + (i & 7)];
              d = __byte_perm(d, v[i], 0x5432);
              asm volatile("" : "+r"(d)::"memory");
            }
          }
          __syncwarp();
          if (ri == 0) w_issue(&maps.wi);
        }
        asm volatile("bar.sync 1, 128;" ::: "memory");
        if (t == 0) PROF_EV(11);
      } else {
        asm volatile("bar.sync 4, 256;" ::: "memory");
        hint_wait(&ws->cntW[0], (ep + 1) * 128u);
        const uint32_t t0 = (uint32_t)clock();
#pragma unroll 1
        for (;;) {
          uint32_t bad = 0;
#pragma unroll
          for (int i = 0; i < 32; i++) {
            const float2 v = ld_x2((const float2*)ws->Wh + (i >> 4) * 2048 + 16 * w + g + 8 * (i & 1) + 64 * q + ((i >> 1) & 7) * 256);
            wf[i] = __float_as_uint(v.x); bad |= __float_as_uint(v.y) ^ tag;
          }
          if (!__any_sync(0xffffffffu, bad & 1)) break;
          spin_guard(t0);
        }
        if (t == 0) PROF_EV(11);
      }
      if (w == 0 && elect_one()) { mbar_expect_tx(bars + 8 * B_W, 8192); bulk_load(sb + OFF_D, dtab, 8192, bars + 8 * B_W); }
      if (!helper) {
        const uint32_t t0 = (uint32_t)clock();
        uint32_t v;
        do { v = ld_x1(ws->gate + rb * 128 + t); spin_guard(t0); } while (__any_sync(0xffffffffu, (v ^ tag) & 1));
        *(uint32_t*)(smem + OFF_G + t * 4) = v;
        __syncwarp();
        mbar_arrive_if(lane == 0, bars + 8 * B_G);
      }
      mbar_wait(bars + 8 * B_W, 0);
      mbar_wait(bars + 8 * B_HX, 0);
      if (t == 0) PROF_EV(12);
      const uint32_t dd = (sb & 0x3FFFF) >> 4;
      const uint64_t dF = d128((dd + (OFF_D >> 4)) | (512u << 16)), dI = d128((dd + (OFF_D >> 4)) | (1u << 16)), dA = d128((dd + (OFF_XB >> 4)) | (512u << 16));
      float az[32];
      const int zero = blockIdx.x >> 16;
      uint32_t pf[32];
#pragma unroll
      for (int mt = 0; mt < 2; mt++) {
        wg_fence();
        if (mt == 0) mma_ss64<0, 3, 0>(az, dA, dF);
        else mma_ss64<0, 3, 2>(az, dA + 512, dF, zero);
#pragma unroll
        for (int k = 1; k < 4; k++) mma_ss64<0, 3, 1>(az, dA + (mt * 512 + k * 128), dF + k * 128);
        wg_commit();
        wg_wait<0>();
        fence_regs<0, 32>(az);
#pragma unroll
        for (int i = 0; i < 16; i++) {
          const float wr = bf_lo(wf[16 * mt + i]), wi = bf_hi(wf[16 * mt + i]);
          pf[16 * mt + i] = pack_pin(fmaf(az[2 * i], wr, -az[2 * i + 1] * wi), fmaf(az[2 * i], wi, az[2 * i + 1] * wr));
        }
      }
      if (t == 0) PROF_EV(16);
#pragma unroll
      for (int mt = 0; mt < 2; mt++) {
        wg_fence();
        mma_rs64<0, 0, 2>(az, pf[16 * mt], pf[16 * mt + 1], pf[16 * mt + 2], pf[16 * mt + 3], dI, mt ? (int)helper : zero);
#pragma unroll
        for (int k = 1; k < 4; k++) mma_rs64<0, 0, 1>(az, pf[16 * mt + 4 * k], pf[16 * mt + 4 * k + 1], pf[16 * mt + 4 * k + 2], pf[16 * mt + 4 * k + 3], dI + k * 2);
        wg_commit();
        wg_wait<0>();
        fence_regs<0, 32>(az);
        if (!helper) {
          const int m = lane >> 3, r = lane & 7;
          const int sl = 2 * (m >> 1) + ((r >> 1) & 1) + 4 * (r >> 2);
          const uint32_t a0 = sb + OFF_XB + (2 * w + (m & 1)) * 2048 + sl * 64 + (((mt * 2 + (r & 1)) ^ (sl >> 1)) << 4);
#pragma unroll
          for (int i = 0; i < 4; i++)
            stsm4t(a0 + i * 512, pack_bf16(az[8 * i], az[8 * i + 1]), pack_bf16(az[8 * i + 2], az[8 * i + 3]), pack_bf16(az[8 * i + 4], az[8 * i + 5]),
                   pack_bf16(az[8 * i + 6], az[8 * i + 7]));
        }
      }
      if (helper) {
#pragma unroll
        for (int i = 0; i < 16; i++) {
          const int n = i >> 1, s0 = 8 * (n >> 1) + 2 * (n & 1) + (q & 1) + 4 * (q >> 1);
          if ((n & 1) == (int)(blockIdx.x & 1)) st_u2(ws->Ts + s0 * 64 + 16 * w + g + 8 * (i & 1), pack_bf16(az[2 * i], az[2 * i + 1]), tag);
        }
        __syncwarp();
        hint_add_if(lane == 0, &ws->cntH[0]);
        if (t == 0) { ws->epoch[blockIdx.x * 8] = ep + 1; PROF_EV(13); }
      } else {
        asm volatile("fence.proxy.async.shared::cta;" ::: "memory");
        __syncwarp();
        if (elect_one()) {
          if (t == 0) PROF_EV(17);
          if (SPACE) __nanosleep(SPACE * w);
          asm volatile("cp.async.bulk.tensor.3d.global.shared::cta.bulk_group [%0, {%2, %3, %4}], [%1];" ::"l"(&maps.ts), "r"(sb + OFF_XB + w * 4096),
                       "r"(32 * kg), "r"(0), "r"(8 * tn + 2 * w) : "memory");
          bulk_done_signal(&ws->cntT[32 * j]);
          if (t == 96) PROF_EV(13);
        }
        __syncwarp();
        if (j == 0) {
          hint_wait(&ws->cntH[0], (ep + 1) * 8u);
          const uint32_t t0 = (uint32_t)clock();
          float2 v;
          do { v = ld_x2((const float2*)ws->Ts + 2 * rb * 64 + t); spin_guard(t0); } while (__any_sync(0xffffffffu, (__float_as_uint(v.y) ^ tag) & 1));
          mbar_wait(bars + 8 * B_TL, 0);
          const uint32_t u = __float_as_uint(v.x);
          *(uint16_t*)(smem + OFF_T + t * 128 + ((t & 7) << 4)) = (uint16_t)u;
          *(uint16_t*)(smem + OFF_T + t * 128 + (((t & 7) ^ 1) << 4)) = (uint16_t)(u >> 16);
          asm volatile("fence.proxy.async.shared::cta;" ::: "memory");
          __syncwarp();
          mbar_arrive_if(lane == 0, bars + 8 * B_T);
        }
      }
    }
  } else {
    asm volatile("setmaxnreg.dec.sync.aligned.u32 24;");
    auto xf_load = [&](int q) {
      const uint32_t fb = bars + 8 * (B_FX + q);
      mbar_expect_tx(fb, U + 8192);
      tma3d(sb + q * U, &maps.x, fb, 64 * q, 0, 2 * rb);
      if (q >= 4) mbar_wait(bars + 8 * (B_FE + ((q - 4) >> 1)), 0);
      tma2d(sb + OFF_XB + (q & 3) * 8192, &maps.ft, fb, 64 * q, 64 * j);
    };
    if (elect_one()) {
      if (warp == 14) {
#pragma unroll
        for (int i = 0; i < B_FT; i++) mbar_init(bars + 8 * i, 1);
        asm volatile("fence.mbarrier_init.release.cluster;" ::: "memory");
        if (!helper) {
#pragma unroll 1
          for (int n = 0; n < 2; n++) {
            const uint32_t fb = bars + 8 * (B_FA + n);
            xf_load(2 * n); xf_load(2 * n + 1);
            mbar_expect_tx(fb, U);
            tma2d(sb + OFF_RING + n * U, &maps.g64, fb, f_full, 64 * n);
            tma2d(sb + OFF_RING + n * U + 8192, &maps.u64, fb, f_full, 64 * n);
          }
        }
      } else if (warp == 15) {
#pragma unroll
        for (int i = B_FT; i < NBAR; i++) mbar_init(bars + 8 * i, i < B_EA ? 1 : i < B_T ? 2 : 4);
#pragma unroll
        for (int i = 0; i < 8; i++) mbar_expect_tx(bars + 8 * (B_Z + i), U / 2);
        asm volatile("fence.mbarrier_init.release.cluster;" ::: "memory");
        asm volatile("fence.proxy.async.shared::cta;" ::: "memory");
      } else if (warp == 13) {
#pragma unroll
        for (int i = 1; i < 4; i++) asm volatile("prefetch.tensormap [%0];" ::"l"((const char*)&maps + i * 128) : "memory");
      }
    }
    __syncwarp();
    asm volatile("bar.arrive 0, 384;" ::: "memory");
    asm volatile("bar.arrive 4, 256;" ::: "memory");
    __syncwarp();
    asm volatile("barrier.cluster.arrive.relaxed.aligned;" ::: "memory");
    asm volatile("bar.sync 3, 128;" ::: "memory");
    if (warp == 15 && !helper) {
        mbar_wait(bars + 8 * B_FE, 0);
        const uint32_t tag = (ld_x1(&ws->epoch[blockIdx.x * 8]) + 1) & 1;
        const int c = lane >> 4, jj = 16 * blockIdx.x + (lane & 15), jm = (2048 - jj) & 2047;
        const unsigned short* pr = (const unsigned short*)w_r + 256 * c;
        const unsigned short* pi = (const unsigned short*)w_i + 256 * c;
        const float wr = 0.25f * (bf_lo(__ldg(pr + jj * 257)) + bf_lo(__ldg(pr + jm * 257)));
        const float wi = 0.25f * (bf_lo(__ldg(pi + jj * 257)) - bf_lo(__ldg(pi + jm * 257)));
        st_u2(ws->Wh + c * 2048 + jj, c ? pack_bf16(-wi, wr) : pack_bf16(wr, wi), tag);
        __syncwarp();
        hint_add_if(lane == 0, &ws->cntW[0]);
      }
    if ((!helper || warp == 15) && elect_one()) {
      if (warp < 14) {
        const int p = warp - 12;
#pragma unroll 1
        for (int n = 2; n < 31; n++) {
          const bool table = n == 4 || n >= 29;
          const int q = n < 4 ? n : n - 1;
          const CUtensorMap* m = table ? &maps.e : n >= 25 ? &maps.g32 + p : &maps.g64 + p;
          const int c0 = table ? 0 : n >= 25 ? f_half : f_full + 64 * (q >> 3);
          const int c1 = table ? (2 * rb + ((n & 1) ^ 1)) * 128 + 64 * p : n >= 25 ? 128 * (n - 25) : 64 * (q & 7);
          const uint32_t fb = bars + 8 * (B_FA + (n & 3)), dst = sb + OFF_RING + (n & 3) * U + p * 8192;
          if (n < 4) mbar_wait(bars + 8 * (B_FE + n - 2), 0);
          else mbar_wait(bars + 8 * (B_EA + (n & 3)), ((n >> 2) & 1) ^ 1);
          tma2d(dst, m, fb, c0, c1);
          if (p == 0) mbar_expect_tx(fb, U);
        }
      } else if (warp == 15) {
        const unsigned ep1 = ld_x1(&ws->epoch[blockIdx.x * 8]) + 1;
        flag_wait(&ws->cntX[helper ? 0 : 32 * j], ep1 * 16u);
        PROF_EV(22);
        mbar_expect_tx(bars + 8 * B_HX, U);
        bulk_load(sb + OFF_XB, ws->X + (size_t)(helper ? 128 : kg * 8 + tn) * 8192, U, bars + 8 * B_HX);
        if (!helper) {
          flag_wait(&ws->cntT[32 * j], ep1 * 64u);
          PROF_EV(23);
          mbar_expect_tx(bars + 8 * B_TL, U);
          tma3d(sb + OFF_T, &maps.t, bars + 8 * B_TL, 64 * j, 0, 2 * rb);
#pragma unroll 1
          for (int i = 0; i < 3; i++) {
            mbar_wait(bars + 8 * (B_PZ + (i >> 1)), 0);
            flag_wait(&ws->cntP[32 * (rb * 8 + j) + i], ep1 * 8u);
            if (i == 2) PROF_EV(26);
            mbar_expect_tx(bars + 8 * (B_HP + i), U);
            bulk_load(sb + i * U, ws->part + (size_t)((rb * 8 + j) * 3 + i) * 1024, U, bars + 8 * (B_HP + i));
          }
          ws->epoch[blockIdx.x * 8] = ep1;
        }
      } else {
#pragma unroll 1
        for (int q = 4; q < 8; q++) xf_load(q);
        mbar_wait(bars + 8 * (B_FE + 2), 0);
        mbar_expect_tx(bars + 8 * B_E0, U);
        tma2d(sb + OFF_XB, &maps.e, bars + 8 * B_E0, 0, 2 * rb * 128);
        tma2d(sb + OFF_XB + 8192, &maps.e, bars + 8 * B_E0, 0, 2 * rb * 128 + 64);
#pragma unroll 1
        for (int h2 = 0; h2 < 2; h2++) {
          const int s0 = 2 * rb + h2, sg = (s0 & ~6) | ((s0 & 2) << 1) | ((s0 & 4) >> 1);
          mbar_wait(bars + 8 * (B_XS + h2), 0);
#pragma unroll 1
          for (int c = 0; c < 2; c++) {
            asm volatile("cp.async.bulk.tensor.4d.global.shared::cta.bulk_group [%0, {%2, %3, %4, %5}], [%1];" ::"l"(&maps.xs),
                         "r"(sb + OFF_XB + h2 * 8192 + c * 4096), "r"(0), "r"(sg), "r"(0), "r"(16 * j + 8 * c) : "memory");
            if (j == 0)
              asm volatile("cp.async.bulk.global.shared::cta.bulk_group [%0], [%1], 256;" ::"l"(ws->X + 128 * 8192 + c * 4096 + sg * 128),
                           "r"(sb + OFF_SP + h2 * 512 + c * 256) : "memory");
            if (SPACE && h2 + c < 2) __nanosleep(SPACE);
          }
        }
        bulk_done_signal(&ws->cntX[32 * j]);
        PROF_EV(20);
        asm volatile("prefetch.tensormap [%0];" ::"l"(&maps.o) : "memory");
#pragma unroll 1
        for (int t = 0; t < 8; t++) {
          const int i = t < 3 ? t + 1 : t < 6 ? t - 2 : 0;
          const int col = 64 * (2 * ((q4 + i) & 3) + ((t < 3 || t == 6) ? 1 - rank : rank));
          const uint32_t fb = bars + 8 * (B_FT + (t & 3)), dst = sb + (t & 3) * TB;
          mbar_wait(bars + 8 * (B_ET + (t == 2 ? 3 : t & 3)), t >> 2);
          mbar_expect_tx(fb, TB);
          tma2d(dst, &maps.d224, fb, col, 224 * j);
          if (t < 2) mbar_wait(bars + 8 * (B_ET + t + 1), 0);
          tma2d(dst + 28672, &maps.ft, fb, col, 64 * j);
        }
      }
    }
  }
}

typedef CUresult (*EncodeFn)(CUtensorMap*, CUtensorMapDataType, cuuint32_t, void*, const cuuint64_t*, const cuuint64_t*, const cuuint32_t*,
                             const cuuint32_t*, CUtensorMapInterleave, CUtensorMapSwizzle, CUtensorMapL2promotion, CUtensorMapFloatOOBfill);

static void encode(EncodeFn f, CUtensorMap* m, const void* base, int rank, const cuuint64_t* dims, const cuuint64_t* strides, const cuuint32_t* box,
                   CUtensorMapSwizzle sw) {
  cuuint32_t es[5] = {1, 1, 1, 1, 1};
  f(m, CU_TENSOR_MAP_DATA_TYPE_BFLOAT16, rank, (void*)base, dims, strides, box, es, CU_TENSOR_MAP_INTERLEAVE_NONE, sw,
    CU_TENSOR_MAP_L2_PROMOTION_L2_128B, CU_TENSOR_MAP_FLOAT_OOB_FILL_NONE);
}

extern "C" void kernel_launch(void* const* d_in, const int* in_sizes, int n_in, void* d_out, int out_size) {
  (void)in_sizes; (void)n_in; (void)out_size;
  const __nv_bfloat16* x = (const __nv_bfloat16*)d_in[0];
  const __nv_bfloat16* w_r = (const __nv_bfloat16*)d_in[1];
  const __nv_bfloat16* w_i = (const __nv_bfloat16*)d_in[2];
  const __nv_bfloat16* Wg = (const __nv_bfloat16*)d_in[4];
  const __nv_bfloat16* Wu = (const __nv_bfloat16*)d_in[5];
  const __nv_bfloat16* Wd = (const __nv_bfloat16*)d_in[6];
  const __nv_bfloat16* gw = (const __nv_bfloat16*)d_in[7];

  void* fp = nullptr; cudaDriverEntryPointQueryResult qr;
  cudaGetDriverEntryPoint("cuTensorMapEncodeTiled", &fp, cudaEnableDefault, &qr);
  EncodeFn enc = (EncodeFn)fp;
  void *pFT, *pET, *pDT, *pW;
  cudaGetSymbolAddress(&pDT, g_DT); cudaGetSymbolAddress(&pW, g_work);
  void *pX = ((Work*)pW)->X, *pT = ((Work*)pW)->T;
  cudaGetSymbolAddress(&pFT, g_FT); cudaGetSymbolAddress(&pET, g_ET);

  Maps mp;
  const CUtensorMapSwizzle S128 = CU_TENSOR_MAP_SWIZZLE_128B, S64 = CU_TENSOR_MAP_SWIZZLE_64B;
  { cuuint64_t d[3] = {512, 64, 32}, s[2] = {32768, 1024}; cuuint32_t b[3] = {64, 64, 2}, b2[3] = {64, 16, 1};
    encode(enc, &mp.x, x, 3, d, s, b, S128); encode(enc, &mp.o, d_out, 3, d, s, b2, S128); }
  { cuuint64_t d[2] = {512, 512}, s[1] = {1024}; cuuint32_t b[2] = {64, 64}; encode(enc, &mp.ft, pFT, 2, d, s, b, S128); }
  { cuuint64_t d[4] = {128, 32, 2, 129}, s[3] = {256, 8192, 16384}; cuuint32_t b[4] = {128, 1, 2, 8}; encode(enc, &mp.xs, pX, 4, d, s, b, CU_TENSOR_MAP_SWIZZLE_NONE); }
  { cuuint64_t d[3] = {512, 32, 64}, s[2] = {65536, 1024}; cuuint32_t b[3] = {32, 32, 2}; encode(enc, &mp.ts, pT, 3, d, s, b, S64); }
  { cuuint64_t d[3] = {512, 64, 32}, s[2] = {1024, 65536}; cuuint32_t b[3] = {64, 64, 2}; encode(enc, &mp.t, pT, 3, d, s, b, S128); }
  { cuuint64_t d[2] = {64, 4096}, s[1] = {128}; cuuint32_t b[2] = {64, 64}; encode(enc, &mp.e, pET, 2, d, s, b, S128); }
  { cuuint64_t d[2] = {1792, 512}, s[1] = {3584}; cuuint32_t b[2] = {64, 64}, b2[2] = {32, 128};
    encode(enc, &mp.g64, Wg, 2, d, s, b, S128); encode(enc, &mp.u64, Wu, 2, d, s, b, S128);
    encode(enc, &mp.g32, Wg, 2, d, s, b2, S64); encode(enc, &mp.u32, Wu, 2, d, s, b2, S64); }
  { cuuint64_t d[2] = {512, 1792}, s[1] = {1024}; cuuint32_t b[2] = {64, 224}; encode(enc, &mp.d224, Wd, 2, d, s, b, S128); }
  { cuuint64_t d[4] = {264, 32, 8, 8}, s[3] = {32896, 512, 4112}; cuuint32_t b[4] = {24, 32, 2, 1};
    encode(enc, &mp.wr, w_r, 4, d, s, b, CU_TENSOR_MAP_SWIZZLE_NONE); encode(enc, &mp.wi, w_i, 4, d, s, b, CU_TENSOR_MAP_SWIZZLE_NONE); }

  cudaFuncSetAttribute(fused_kernel, cudaFuncAttributeMaxDynamicSharedMemorySize, SMEM_BYTES);
  fused_kernel<<<NCTA, 512, SMEM_BYTES>>>((Work*)pW, (const uint16_t*)pDT, w_r, w_i, gw, mp);
}
```

```cpp
#include <cuda_runtime.h>
#include <cuda_bf16.h>
#include <cuda.h>
#include <stdint.h>

namespace tbl {
constexpr double PI = 3.14159265358979323846264338327950288;
constexpr double sin_s(double x) { double t = x, s = x; for (int n = 1; n < 12; n++) { t *= -x * x / ((2 * n) * (2 * n + 1)); s += t; } return s; }
constexpr double cos_s(double x) { double t = 1, s = 1; for (int n = 1; n < 12; n++) { t *= -x * x / ((2 * n - 1) * (2 * n)); s += t; } return s; }
constexpr double cos2048(int m) {
  m &= 2047; if (m > 1024) m = 2048 - m;
  bool neg = false; if (m > 512) { m = 1024 - m; neg = true; }
  double v = (m <= 256) ? cos_s(2 * PI * m / 2048) : sin_s(2 * PI * (512 - m) / 2048);
  return neg ? -v : v;
}
constexpr uint16_t to_bf16(double v) {
  if (v == 0) return 0;
  uint16_t s = 0; if (v < 0) { s = 0x8000; v = -v; }
  int e = 0; while (v >= 2) { v /= 2; e++; } while (v < 1) { v *= 2; e--; }
  double m = (v - 1) * 128; int mi = (int)m; double fr = m - mi;
  if (fr > 0.5 || (fr == 0.5 && (mi & 1))) mi++;
  if (mi == 128) { mi = 0; e++; }
  return (uint16_t)(s | ((e + 127) << 7) | mi);
}
struct CosT { uint16_t v[2048]; constexpr CosT() : v() { for (int i = 0; i < 2048; i++) v[i] = to_bf16(cos2048(i)); } };
struct alignas(1024) FT {
  uint16_t v[512 * 512];
  constexpr FT() : v() {
    CosT c;
    for (int r = 0; r < 512; r++) {
      int k = (r >> 4) * 8 + (r & 7), e = (r >> 3) & 1;
      int mul = 4 * k, add = e ? 512 : 0;
      if (k == 0 && e == 1) { mul = 1024; add = 0; }
      for (int d = 0; d < 512; d++) v[r * 512 + d] = c.v[(d * mul + add) & 2047];
    }
  }
};
struct alignas(1024) ET {
  uint16_t v[2048 * 128];
  constexpr ET() : v() {
    CosT c;
    for (int s = 0; s < 2048; s++)
      for (int j = 0; j < 64; j++) {
        const int o = (s & 31) * 8192 + (s >> 5) * 64 + j;
        v[o] = c.v[(s * j) & 2047]; v[o + 4096] = c.v[(s * j + 512) & 2047];
      }
  }
};
struct alignas(1024) DT {
  uint16_t v[64 * 64];
  constexpr DT() : v() {
    CosT c;
    for (int r = 0; r < 64; r++)
      for (int n = 0; n < 64; n++) {
        const int sg = r >> 1, s0 = (sg & ~6) | ((sg & 2) << 1) | ((sg & 4) >> 1), e = r & 1, f = n & 1;
        const int m = 64 * s0 * (n >> 1) + (e == f ? 0 : e ? -512 : 512);
        v[r * 64 + (((n >> 3) ^ (r & 7)) << 3) + (n & 7)] = c.v[m & 2047];
      }
  }
};
}

__device__ constexpr tbl::FT g_FT = tbl::FT();
__device__ constexpr tbl::ET g_ET = tbl::ET();
__device__ constexpr tbl::DT g_DT = tbl::DT();

struct alignas(1024) Work {
  unsigned epoch[132 * 8];
  unsigned cntX[8 * 32], cntT[8 * 32], cntP[128 * 32], cntW[32], cntH[32];
  alignas(16) float gate[16 * 128];
  alignas(16) uint2 Wh[2 * 2048];
  alignas(16) uint2 Ts[32 * 64];
  alignas(1024) uint16_t X[129 * 8192];
  alignas(1024) uint16_t T[32 * 64 * 512];
  alignas(1024) uint4 part[128 * 3 * 1024];
};
__device__ Work g_work;
#define PROF_EV(i) do {} while (0)
#define PROF_CK(i) do {} while (0)

__device__ __forceinline__ uint32_t smem_u32(const void* p) { return (uint32_t)__cvta_generic_to_shared(p); }
__device__ __forceinline__ void mbar_init(uint32_t bar, uint32_t cnt) { asm volatile("mbarrier.init.shared::cta.b64 [%0], %1;" ::"r"(bar), "r"(cnt)); }
__device__ __forceinline__ void mbar_expect_tx(uint32_t bar, uint32_t bytes) { asm volatile("mbarrier.arrive.expect_tx.shared::cta.b64 _, [%0], %1;" ::"r"(bar), "r"(bytes) : "memory"); }
__device__ __forceinline__ void mbar_arrive(uint32_t bar) { asm volatile("mbarrier.arrive.shared::cta.b64 _, [%0];" ::"r"(bar) : "memory"); }
__device__ __forceinline__ bool elect_one() {
  uint32_t p;
  asm volatile("{\n.reg .pred p;\nelect.sync _|p, 0xffffffff;\nselp.u32 %0, 1, 0, p;\n}" : "=r"(p));
  return p;
}
__device__ __forceinline__ void mbar_arrive_if(bool p, uint32_t bar) {
  asm volatile("{\n.reg .pred p;\nsetp.ne.b32 p, %1, 0;\n@p mbarrier.arrive.shared::cta.b64 _, [%0];\n}" ::"r"(bar), "r"((int)p) : "memory");
}
__device__ __forceinline__ void hint_add_if(bool p, unsigned* a) {
  asm volatile("{\n.reg .pred p;\nsetp.ne.b32 p, %1, 0;\n@p red.relaxed.gpu.global.add.u32 [%0], 1;\n}" ::"l"(a), "r"((int)p) : "memory");
}
__device__ __forceinline__ bool mbar_try(uint32_t bar, uint32_t parity) {
  uint32_t ok;
  asm volatile("{\n.reg .pred p;\nmbarrier.test_wait.parity.shared::cta.b64 p, [%1], %2;\nselp.u32 %0, 1, 0, p;\n}" : "=r"(ok) : "r"(bar), "r"(parity) : "memory");
  return ok;
}
__device__ __forceinline__ void mbar_wait(uint32_t bar, uint32_t parity) {
  asm volatile(
      "{\n.reg .pred p;\n.reg .u32 n;\nmov.u32 n, 0;\n"
      "W_LOOP:\nmbarrier.try_wait.parity.shared::cta.b64 p, [%0], %1;\n@p bra W_DONE;\n"
      "add.u32 n, n, 1;\nsetp.lt.u32 p, n, 0x40000;\n@p bra W_LOOP;\ntrap;\nW_DONE:\n}" ::"r"(bar), "r"(parity) : "memory");
}
__device__ __forceinline__ void bulk_load(uint32_t dst, const void* src, uint32_t bytes, uint32_t bar) {
  asm volatile("cp.async.bulk.shared::cluster.global.mbarrier::complete_tx::bytes [%0], [%1], %2, [%3];" ::"r"(dst), "l"(src), "r"(bytes), "r"(bar) : "memory");
}
__device__ __forceinline__ void cp16(uint32_t dst, const void* src) { asm volatile("cp.async.cg.shared.global [%0], [%1], 16;" ::"r"(dst), "l"(src) : "memory"); }
__device__ __forceinline__ void spin_guard(uint32_t t0) { if ((uint32_t)clock() - t0 > (1u << 30)) __trap(); }
__device__ __forceinline__ float tagf(float v, uint32_t tag) { return __uint_as_float((__float_as_uint(v) & ~1u) | tag); }
__device__ __forceinline__ float untag(float v) { return __uint_as_float(__float_as_uint(v) & ~1u); }
__device__ __forceinline__ void st_x2(float2* p, float a, float b) { asm volatile("st.relaxed.gpu.global.v2.f32 [%0], {%1,%2};" ::"l"(p), "f"(a), "f"(b) : "memory"); }
__device__ __forceinline__ float2 ld_x2(const float2* p) { float2 v; asm volatile("ld.relaxed.gpu.global.v2.f32 {%0,%1}, [%2];" : "=f"(v.x), "=f"(v.y) : "l"(p) : "memory"); return v; }
__device__ __forceinline__ void st_u2(uint2* p, uint32_t a, uint32_t b) { asm volatile("st.relaxed.gpu.global.v2.u32 [%0], {%1,%2};" ::"l"(p), "r"(a), "r"(b) : "memory"); }
__device__ __forceinline__ void prefetch2d(const CUtensorMap* m, int c0, int c1) { asm volatile("cp.async.bulk.prefetch.tensor.2d.L2.global [%0, {%1, %2}];" ::"l"(m), "r"(c0), "r"(c1) : "memory"); }
__device__ __forceinline__ void prefetch1d(const void* p, uint32_t bytes) { asm volatile("cp.async.bulk.prefetch.L2.global [%0], %1;" ::"l"(p), "r"(bytes) : "memory"); }
__device__ __forceinline__ uint32_t ld_x1(const void* p) { uint32_t v; asm volatile("ld.relaxed.gpu.global.u32 %0, [%1];" : "=r"(v) : "l"(p) : "memory"); return v; }
__device__ __forceinline__ uint4 ld_x4(const void* p) { uint4 v; asm volatile("ld.relaxed.gpu.global.v4.u32 {%0,%1,%2,%3}, [%4];" : "=r"(v.x), "=r"(v.y), "=r"(v.z), "=r"(v.w) : "l"(p) : "memory"); return v; }
__device__ __forceinline__ void st_x4(void* p, uint32_t a, uint32_t b, uint32_t c, uint32_t d) { asm volatile("st.relaxed.gpu.global.v4.u32 [%0], {%1,%2,%3,%4};" ::"l"(p), "r"(a), "r"(b), "r"(c), "r"(d) : "memory"); }
__device__ __forceinline__ uint32_t mapa(uint32_t a, uint32_t cta) { uint32_t r; asm volatile("mapa.shared::cluster.u32 %0, %1, %2;" : "=r"(r) : "r"(a), "r"(cta)); return r; }
__device__ __forceinline__ void stsm4t(uint32_t a, uint32_t r0, uint32_t r1, uint32_t r2, uint32_t r3) {
  asm volatile("stmatrix.sync.aligned.m8n8.x4.trans.shared.b16 [%0], {%1,%2,%3,%4};" ::"r"(a), "r"(r0), "r"(r1), "r"(r2), "r"(r3) : "memory");
}
__device__ __forceinline__ void hint_add(unsigned* p) { asm volatile("red.relaxed.gpu.global.add.u32 [%0], 1;" ::"l"(p) : "memory"); }
__device__ __forceinline__ void hint_wait(const unsigned* p, unsigned target) {
  const uint32_t t0 = (uint32_t)clock();
  while ((int)(ld_x1(p) - target) < 0) spin_guard(t0);
}
__device__ __forceinline__ void bulk_done_signal(unsigned* p) {
  asm volatile("cp.async.bulk.commit_group;\ncp.async.bulk.wait_group 0;\nfence.proxy.async.global;" ::: "memory");
  hint_add(p);
}
__device__ __forceinline__ void flag_wait(const unsigned* p, unsigned target) {
  hint_wait(p, target);
  asm volatile("fence.proxy.async.global;" ::: "memory");
}
__device__ __forceinline__ void tma2d(uint32_t dst, const CUtensorMap* m, uint32_t bar, int c0, int c1) {
  asm volatile("cp.async.bulk.tensor.2d.shared::cluster.global.mbarrier::complete_tx::bytes [%0], [%1, {%3, %4}], [%2];" ::"r"(dst), "l"(m), "r"(bar), "r"(c0), "r"(c1) : "memory");
}
__device__ __forceinline__ void tma3d(uint32_t dst, const CUtensorMap* m, uint32_t bar, int c0, int c1, int c2) {
  asm volatile("cp.async.bulk.tensor.3d.shared::cluster.global.mbarrier::complete_tx::bytes [%0], [%1, {%3, %4, %5}], [%2];" ::"r"(dst), "l"(m), "r"(bar), "r"(c0), "r"(c1), "r"(c2) : "memory");
}
__device__ __forceinline__ void tma4d(uint32_t dst, const CUtensorMap* m, uint32_t bar, int c0, int c1, int c2, int c3) {
  asm volatile("cp.async.bulk.tensor.4d.shared::cluster.global.mbarrier::complete_tx::bytes [%0], [%1, {%3, %4, %5, %6}], [%2];" ::"r"(dst), "l"(m), "r"(bar), "r"(c0), "r"(c1), "r"(c2), "r"(c3) : "memory");
}
__device__ __forceinline__ void wg_fence() { asm volatile("wgmma.fence.sync.aligned;" ::: "memory"); }
__device__ __forceinline__ void wg_commit() { asm volatile("wgmma.commit_group.sync.aligned;" ::: "memory"); }
template <int N> __device__ __forceinline__ void wg_wait() { asm volatile("wgmma.wait_group.sync.aligned %0;" ::"n"(N) : "memory"); }
template <int O, int N, int NN> __device__ __forceinline__ void fence_regs(float (&d)[NN]) {
#pragma unroll
  for (int i = 0; i < N; i++) asm volatile("" : "+f"(d[O + i])::"memory");
}
__device__ __forceinline__ uint32_t pack_bf16(float lo, float hi) {
  uint32_t r; asm("cvt.rn.bf16x2.f32 %0, %1, %2;" : "=r"(r) : "f"(hi), "f"(lo)); return r;
}
__device__ __forceinline__ uint32_t pack_pin(float lo, float hi) {
  uint32_t r; asm volatile("cvt.rn.bf16x2.f32 %0, %1, %2;" : "=r"(r) : "f"(hi), "f"(lo) : "memory"); return r;
}
__device__ __forceinline__ float bf_lo(uint32_t u) { return __uint_as_float(u << 16); }
__device__ __forceinline__ float bf_hi(uint32_t u) { return __uint_as_float(u & 0xffff0000u); }

__device__ __forceinline__ uint64_t d128(uint32_t lo) { uint64_t d; asm("mov.b64 %0, {%1, 0x40000040};" : "=l"(d) : "r"(lo)); return d; }
__device__ __forceinline__ uint64_t d64(uint32_t lo) { uint64_t d; asm("mov.b64 %0, {%1, 0x80000020};" : "=l"(d) : "r"(lo)); return d; }
template<int O,int TB,int ACC,int NN> __device__ __forceinline__ void mma_ss64(float (&d)[NN], uint64_t da, uint64_t db, int sd = 0){
  if constexpr (ACC == 1) asm volatile("wgmma.mma_async.sync.aligned.m64n64k16.f32.bf16.bf16 {%0,%1,%2,%3,%4,%5,%6,%7,%8,%9,%10,%11,%12,%13,%14,%15,%16,%17,%18,%19,%20,%21,%22,%23,%24,%25,%26,%27,%28,%29,%30,%31}, %32, %33, 1, 1, 1, %35, %34;"
   : "+f"(d[O+0]), "+f"(d[O+1]), "+f"(d[O+2]), "+f"(d[O+3]), "+f"(d[O+4]), "+f"(d[O+5]), "+f"(d[O+6]), "+f"(d[O+7]), "+f"(d[O+8]), "+f"(d[O+9]), "+f"(d[O+10]), "+f"(d[O+11]), "+f"(d[O+12]), "+f"(d[O+13]), "+f"(d[O+14]), "+f"(d[O+15]), "+f"(d[O+16]), "+f"(d[O+17]), "+f"(d[O+18]), "+f"(d[O+19]), "+f"(d[O+20]), "+f"(d[O+21]), "+f"(d[O+22]), "+f"(d[O+23]), "+f"(d[O+24]), "+f"(d[O+25]), "+f"(d[O+26]), "+f"(d[O+27]), "+f"(d[O+28]), "+f"(d[O+29]), "+f"(d[O+30]), "+f"(d[O+31])
   : "l"(da), "l"(db), "n"(TB & 1), "n"(TB >> 1));
  else if constexpr (ACC == 0) asm volatile("wgmma.mma_async.sync.aligned.m64n64k16.f32.bf16.bf16 {%0,%1,%2,%3,%4,%5,%6,%7,%8,%9,%10,%11,%12,%13,%14,%15,%16,%17,%18,%19,%20,%21,%22,%23,%24,%25,%26,%27,%28,%29,%30,%31}, %32, %33, 0, 1, 1, %35, %34;"
   : "=f"(d[O+0]), "=f"(d[O+1]), "=f"(d[O+2]), "=f"(d[O+3]), "=f"(d[O+4]), "=f"(d[O+5]), "=f"(d[O+6]), "=f"(d[O+7]), "=f"(d[O+8]), "=f"(d[O+9]), "=f"(d[O+10]), "=f"(d[O+11]), "=f"(d[O+12]), "=f"(d[O+13]), "=f"(d[O+14]), "=f"(d[O+15]), "=f"(d[O+16]), "=f"(d[O+17]), "=f"(d[O+18]), "=f"(d[O+19]), "=f"(d[O+20]), "=f"(d[O+21]), "=f"(d[O+22]), "=f"(d[O+23]), "=f"(d[O+24]), "=f"(d[O+25]), "=f"(d[O+26]), "=f"(d[O+27]), "=f"(d[O+28]), "=f"(d[O+29]), "=f"(d[O+30]), "=f"(d[O+31])
   : "l"(da), "l"(db), "n"(TB & 1), "n"(TB >> 1));
  else asm volatile("{\n.reg .pred p;\nsetp.ne.b32 p, %36, 0;\nwgmma.mma_async.sync.aligned.m64n64k16.f32.bf16.bf16 {%0,%1,%2,%3,%4,%5,%6,%7,%8,%9,%10,%11,%12,%13,%14,%15,%16,%17,%18,%19,%20,%21,%22,%23,%24,%25,%26,%27,%28,%29,%30,%31}, %32, %33, p, 1, 1, %35, %34;\n}"
   : "+f"(d[O+0]), "+f"(d[O+1]), "+f"(d[O+2]), "+f"(d[O+3]), "+f"(d[O+4]), "+f"(d[O+5]), "+f"(d[O+6]), "+f"(d[O+7]), "+f"(d[O+8]), "+f"(d[O+9]), "+f"(d[O+10]), "+f"(d[O+11]), "+f"(d[O+12]), "+f"(d[O+13]), "+f"(d[O+14]), "+f"(d[O+15]), "+f"(d[O+16]), "+f"(d[O+17]), "+f"(d[O+18]), "+f"(d[O+19]), "+f"(d[O+20]), "+f"(d[O+21]), "+f"(d[O+22]), "+f"(d[O+23]), "+f"(d[O+24]), "+f"(d[O+25]), "+f"(d[O+26]), "+f"(d[O+27]), "+f"(d[O+28]), "+f"(d[O+29]), "+f"(d[O+30]), "+f"(d[O+31])
   : "l"(da), "l"(db), "n"(TB & 1), "n"(TB >> 1), "r"(sd));
}
template<int O,int TB,int ACC,int NN> __device__ __forceinline__ void mma_rs64(float (&d)[NN], uint32_t a0, uint32_t a1, uint32_t a2, uint32_t a3, uint64_t db, int sd = 0){
  if constexpr (ACC == 1) asm volatile("wgmma.mma_async.sync.aligned.m64n64k16.f32.bf16.bf16 {%0,%1,%2,%3,%4,%5,%6,%7,%8,%9,%10,%11,%12,%13,%14,%15,%16,%17,%18,%19,%20,%21,%22,%23,%24,%25,%26,%27,%28,%29,%30,%31}, {%32,%33,%34,%35}, %36, 1, 1, 1, %37;"
   : "+f"(d[O+0]), "+f"(d[O+1]), "+f"(d[O+2]), "+f"(d[O+3]), "+f"(d[O+4]), "+f"(d[O+5]), "+f"(d[O+6]), "+f"(d[O+7]), "+f"(d[O+8]), "+f"(d[O+9]), "+f"(d[O+10]), "+f"(d[O+11]), "+f"(d[O+12]), "+f"(d[O+13]), "+f"(d[O+14]), "+f"(d[O+15]), "+f"(d[O+16]), "+f"(d[O+17]), "+f"(d[O+18]), "+f"(d[O+19]), "+f"(d[O+20]), "+f"(d[O+21]), "+f"(d[O+22]), "+f"(d[O+23]), "+f"(d[O+24]), "+f"(d[O+25]), "+f"(d[O+26]), "+f"(d[O+27]), "+f"(d[O+28]), "+f"(d[O+29]), "+f"(d[O+30]), "+f"(d[O+31])
   : "r"(a0), "r"(a1), "r"(a2), "r"(a3), "l"(db), "n"(TB));
  else if constexpr (ACC == 0) asm volatile("wgmma.mma_async.sync.aligned.m64n64k16.f32.bf16.bf16 {%0,%1,%2,%3,%4,%5,%6,%7,%8,%9,%10,%11,%12,%13,%14,%15,%16,%17,%18,%19,%20,%21,%22,%23,%24,%25,%26,%27,%28,%29,%30,%31}, {%32,%33,%34,%35}, %36, 0, 1, 1, %37;"
   : "=f"(d[O+0]), "=f"(d[O+1]), "=f"(d[O+2]), "=f"(d[O+3]), "=f"(d[O+4]), "=f"(d[O+5]), "=f"(d[O+6]), "=f"(d[O+7]), "=f"(d[O+8]), "=f"(d[O+9]), "=f"(d[O+10]), "=f"(d[O+11]), "=f"(d[O+12]), "=f"(d[O+13]), "=f"(d[O+14]), "=f"(d[O+15]), "=f"(d[O+16]), "=f"(d[O+17]), "=f"(d[O+18]), "=f"(d[O+19]), "=f"(d[O+20]), "=f"(d[O+21]), "=f"(d[O+22]), "=f"(d[O+23]), "=f"(d[O+24]), "=f"(d[O+25]), "=f"(d[O+26]), "=f"(d[O+27]), "=f"(d[O+28]), "=f"(d[O+29]), "=f"(d[O+30]), "=f"(d[O+31])
   : "r"(a0), "r"(a1), "r"(a2), "r"(a3), "l"(db), "n"(TB));
  else asm volatile("{\n.reg .pred p;\nsetp.ne.b32 p, %38, 0;\nwgmma.mma_async.sync.aligned.m64n64k16.f32.bf16.bf16 {%0,%1,%2,%3,%4,%5,%6,%7,%8,%9,%10,%11,%12,%13,%14,%15,%16,%17,%18,%19,%20,%21,%22,%23,%24,%25,%26,%27,%28,%29,%30,%31}, {%32,%33,%34,%35}, %36, p, 1, 1, %37;\n}"
   : "+f"(d[O+0]), "+f"(d[O+1]), "+f"(d[O+2]), "+f"(d[O+3]), "+f"(d[O+4]), "+f"(d[O+5]), "+f"(d[O+6]), "+f"(d[O+7]), "+f"(d[O+8]), "+f"(d[O+9]), "+f"(d[O+10]), "+f"(d[O+11]), "+f"(d[O+12]), "+f"(d[O+13]), "+f"(d[O+14]), "+f"(d[O+15]), "+f"(d[O+16]), "+f"(d[O+17]), "+f"(d[O+18]), "+f"(d[O+19]), "+f"(d[O+20]), "+f"(d[O+21]), "+f"(d[O+22]), "+f"(d[O+23]), "+f"(d[O+24]), "+f"(d[O+25]), "+f"(d[O+26]), "+f"(d[O+27]), "+f"(d[O+28]), "+f"(d[O+29]), "+f"(d[O+30]), "+f"(d[O+31])
   : "r"(a0), "r"(a1), "r"(a2), "r"(a3), "l"(db), "n"(TB), "r"(sd));
}
template<int O,int TB,int ACC,int NN> __device__ __forceinline__ void mma_ss128(float (&d)[NN], uint64_t da, uint64_t db, int sd = 0){
  if constexpr (ACC == 1) asm volatile("wgmma.mma_async.sync.aligned.m64n128k16.f32.bf16.bf16 {%0,%1,%2,%3,%4,%5,%6,%7,%8,%9,%10,%11,%12,%13,%14,%15,%16,%17,%18,%19,%20,%21,%22,%23,%24,%25,%26,%27,%28,%29,%30,%31,%32,%33,%34,%35,%36,%37,%38,%39,%40,%41,%42,%43,%44,%45,%46,%47,%48,%49,%50,%51,%52,%53,%54,%55,%56,%57,%58,%59,%60,%61,%62,%63}, %64, %65, 1, 1, 1, %67, %66;"
   : "+f"(d[O+0]), "+f"(d[O+1]), "+f"(d[O+2]), "+f"(d[O+3]), "+f"(d[O+4]), "+f"(d[O+5]), "+f"(d[O+6]), "+f"(d[O+7]), "+f"(d[O+8]), "+f"(d[O+9]), "+f"(d[O+10]), "+f"(d[O+11]), "+f"(d[O+12]), "+f"(d[O+13]), "+f"(d[O+14]), "+f"(d[O+15]), "+f"(d[O+16]), "+f"(d[O+17]), "+f"(d[O+18]), "+f"(d[O+19]), "+f"(d[O+20]), "+f"(d[O+21]), "+f"(d[O+22]), "+f"(d[O+23]), "+f"(d[O+24]), "+f"(d[O+25]), "+f"(d[O+26]), "+f"(d[O+27]), "+f"(d[O+28]), "+f"(d[O+29]), "+f"(d[O+30]), "+f"(d[O+31]), "+f"(d[O+32]), "+f"(d[O+33]), "+f"(d[O+34]), "+f"(d[O+35]), "+f"(d[O+36]), "+f"(d[O+37]), "+f"(d[O+38]), "+f"(d[O+39]), "+f"(d[O+40]), "+f"(d[O+41]), "+f"(d[O+42]), "+f"(d[O+43]), "+f"(d[O+44]), "+f"(d[O+45]), "+f"(d[O+46]), "+f"(d[O+47]), "+f"(d[O+48]), "+f"(d[O+49]), "+f"(d[O+50]), "+f"(d[O+51]), "+f"(d[O+52]), "+f"(d[O+53]), "+f"(d[O+54]), "+f"(d[O+55]), "+f"(d[O+56]), "+f"(d[O+57]), "+f"(d[O+58]), "+f"(d[O+59]), "+f"(d[O+60]), "+f"(d[O+61]), "+f"(d[O+62]), "+f"(d[O+63])
   : "l"(da), "l"(db), "n"(TB & 1), "n"(TB >> 1));
  else if constexpr (ACC == 0) asm volatile("wgmma.mma_async.sync.aligned.m64n128k16.f32.bf16.bf16 {%0,%1,%2,%3,%4,%5,%6,%7,%8,%9,%10,%11,%12,%13,%14,%15,%16,%17,%18,%19,%20,%21,%22,%23,%24,%25,%26,%27,%28,%29,%30,%31,%32,%33,%34,%35,%36,%37,%38,%39,%40,%41,%42,%43,%44,%45,%46,%47,%48,%49,%50,%51,%52,%53,%54,%55,%56,%57,%58,%59,%60,%61,%62,%63}, %64, %65, 0, 1, 1, %67, %66;"
   : "=f"(d[O+0]), "=f"(d[O+1]), "=f"(d[O+2]), "=f"(d[O+3]), "=f"(d[O+4]), "=f"(d[O+5]), "=f"(d[O+6]), "=f"(d[O+7]), "=f"(d[O+8]), "=f"(d[O+9]), "=f"(d[O+10]), "=f"(d[O+11]), "=f"(d[O+12]), "=f"(d[O+13]), "=f"(d[O+14]), "=f"(d[O+15]), "=f"(d[O+16]), "=f"(d[O+17]), "=f"(d[O+18]), "=f"(d[O+19]), "=f"(d[O+20]), "=f"(d[O+21]), "=f"(d[O+22]), "=f"(d[O+23]), "=f"(d[O+24]), "=f"(d[O+25]), "=f"(d[O+26]), "=f"(d[O+27]), "=f"(d[O+28]), "=f"(d[O+29]), "=f"(d[O+30]), "=f"(d[O+31]), "=f"(d[O+32]), "=f"(d[O+33]), "=f"(d[O+34]), "=f"(d[O+35]), "=f"(d[O+36]), "=f"(d[O+37]), "=f"(d[O+38]), "=f"(d[O+39]), "=f"(d[O+40]), "=f"(d[O+41]), "=f"(d[O+42]), "=f"(d[O+43]), "=f"(d[O+44]), "=f"(d[O+45]), "=f"(d[O+46]), "=f"(d[O+47]), "=f"(d[O+48]), "=f"(d[O+49]), "=f"(d[O+50]), "=f"(d[O+51]), "=f"(d[O+52]), "=f"(d[O+53]), "=f"(d[O+54]), "=f"(d[O+55]), "=f"(d[O+56]), "=f"(d[O+57]), "=f"(d[O+58]), "=f"(d[O+59]), "=f"(d[O+60]), "=f"(d[O+61]), "=f"(d[O+62]), "=f"(d[O+63])
   : "l"(da), "l"(db), "n"(TB & 1), "n"(TB >> 1));
  else asm volatile("{\n.reg .pred p;\nsetp.ne.b32 p, %68, 0;\nwgmma.mma_async.sync.aligned.m64n128k16.f32.bf16.bf16 {%0,%1,%2,%3,%4,%5,%6,%7,%8,%9,%10,%11,%12,%13,%14,%15,%16,%17,%18,%19,%20,%21,%22,%23,%24,%25,%26,%27,%28,%29,%30,%31,%32,%33,%34,%35,%36,%37,%38,%39,%40,%41,%42,%43,%44,%45,%46,%47,%48,%49,%50,%51,%52,%53,%54,%55,%56,%57,%58,%59,%60,%61,%62,%63}, %64, %65, p, 1, 1, %67, %66;\n}"
   : "+f"(d[O+0]), "+f"(d[O+1]), "+f"(d[O+2]), "+f"(d[O+3]), "+f"(d[O+4]), "+f"(d[O+5]), "+f"(d[O+6]), "+f"(d[O+7]), "+f"(d[O+8]), "+f"(d[O+9]), "+f"(d[O+10]), "+f"(d[O+11]), "+f"(d[O+12]), "+f"(d[O+13]), "+f"(d[O+14]), "+f"(d[O+15]), "+f"(d[O+16]), "+f"(d[O+17]), "+f"(d[O+18]), "+f"(d[O+19]), "+f"(d[O+20]), "+f"(d[O+21]), "+f"(d[O+22]), "+f"(d[O+23]), "+f"(d[O+24]), "+f"(d[O+25]), "+f"(d[O+26]), "+f"(d[O+27]), "+f"(d[O+28]), "+f"(d[O+29]), "+f"(d[O+30]), "+f"(d[O+31]), "+f"(d[O+32]), "+f"(d[O+33]), "+f"(d[O+34]), "+f"(d[O+35]), "+f"(d[O+36]), "+f"(d[O+37]), "+f"(d[O+38]), "+f"(d[O+39]), "+f"(d[O+40]), "+f"(d[O+41]), "+f"(d[O+42]), "+f"(d[O+43]), "+f"(d[O+44]), "+f"(d[O+45]), "+f"(d[O+46]), "+f"(d[O+47]), "+f"(d[O+48]), "+f"(d[O+49]), "+f"(d[O+50]), "+f"(d[O+51]), "+f"(d[O+52]), "+f"(d[O+53]), "+f"(d[O+54]), "+f"(d[O+55]), "+f"(d[O+56]), "+f"(d[O+57]), "+f"(d[O+58]), "+f"(d[O+59]), "+f"(d[O+60]), "+f"(d[O+61]), "+f"(d[O+62]), "+f"(d[O+63])
   : "l"(da), "l"(db), "n"(TB & 1), "n"(TB >> 1), "r"(sd));
}
template<int O,int TB,int ACC,int NN> __device__ __forceinline__ void mma_rs128(float (&d)[NN], uint32_t a0, uint32_t a1, uint32_t a2, uint32_t a3, uint64_t db, int sd = 0){
  if constexpr (ACC == 1) asm volatile("wgmma.mma_async.sync.aligned.m64n128k16.f32.bf16.bf16 {%0,%1,%2,%3,%4,%5,%6,%7,%8,%9,%10,%11,%12,%13,%14,%15,%16,%17,%18,%19,%20,%21,%22,%23,%24,%25,%26,%27,%28,%29,%30,%31,%32,%33,%34,%35,%36,%37,%38,%39,%40,%41,%42,%43,%44,%45,%46,%47,%48,%49,%50,%51,%52,%53,%54,%55,%56,%57,%58,%59,%60,%61,%62,%63}, {%64,%65,%66,%67}, %68, 1, 1, 1, %69;"
   : "+f"(d[O+0]), "+f"(d[O+1]), "+f"(d[O+2]), "+f"(d[O+3]), "+f"(d[O+4]), "+f"(d[O+5]), "+f"(d[O+6]), "+f"(d[O+7]), "+f"(d[O+8]), "+f"(d[O+9]), "+f"(d[O+10]), "+f"(d[O+11]), "+f"(d[O+12]), "+f"(d[O+13]), "+f"(d[O+14]), "+f"(d[O+15]), "+f"(d[O+16]), "+f"(d[O+17]), "+f"(d[O+18]), "+f"(d[O+19]), "+f"(d[O+20]), "+f"(d[O+21]), "+f"(d[O+22]), "+f"(d[O+23]), "+f"(d[O+24]), "+f"(d[O+25]), "+f"(d[O+26]), "+f"(d[O+27]), "+f"(d[O+28]), "+f"(d[O+29]), "+f"(d[O+30]), "+f"(d[O+31]), "+f"(d[O+32]), "+f"(d[O+33]), "+f"(d[O+34]), "+f"(d[O+35]), "+f"(d[O+36]), "+f"(d[O+37]), "+f"(d[O+38]), "+f"(d[O+39]), "+f"(d[O+40]), "+f"(d[O+41]), "+f"(d[O+42]), "+f"(d[O+43]), "+f"(d[O+44]), "+f"(d[O+45]), "+f"(d[O+46]), "+f"(d[O+47]), "+f"(d[O+48]), "+f"(d[O+49]), "+f"(d[O+50]), "+f"(d[O+51]), "+f"(d[O+52]), "+f"(d[O+53]), "+f"(d[O+54]), "+f"(d[O+55]), "+f"(d[O+56]), "+f"(d[O+57]), "+f"(d[O+58]), "+f"(d[O+59]), "+f"(d[O+60]), "+f"(d[O+61]), "+f"(d[O+62]), "+f"(d[O+63])
   : "r"(a0), "r"(a1), "r"(a2), "r"(a3), "l"(db), "n"(TB));
  else if constexpr (ACC == 0) asm volatile("wgmma.mma_async.sync.aligned.m64n128k16.f32.bf16.bf16 {%0,%1,%2,%3,%4,%5,%6,%7,%8,%9,%10,%11,%12,%13,%14,%15,%16,%17,%18,%19,%20,%21,%22,%23,%24,%25,%26,%27,%28,%29,%30,%31,%32,%33,%34,%35,%36,%37,%38,%39,%40,%41,%42,%43,%44,%45,%46,%47,%48,%49,%50,%51,%52,%53,%54,%55,%56,%57,%58,%59,%60,%61,%62,%63}, {%64,%65,%66,%67}, %68, 0, 1, 1, %69;"
   : "=f"(d[O+0]), "=f"(d[O+1]), "=f"(d[O+2]), "=f"(d[O+3]), "=f"(d[O+4]), "=f"(d[O+5]), "=f"(d[O+6]), "=f"(d[O+7]), "=f"(d[O+8]), "=f"(d[O+9]), "=f"(d[O+10]), "=f"(d[O+11]), "=f"(d[O+12]), "=f"(d[O+13]), "=f"(d[O+14]), "=f"(d[O+15]), "=f"(d[O+16]), "=f"(d[O+17]), "=f"(d[O+18]), "=f"(d[O+19]), "=f"(d[O+20]), "=f"(d[O+21]), "=f"(d[O+22]), "=f"(d[O+23]), "=f"(d[O+24]), "=f"(d[O+25]), "=f"(d[O+26]), "=f"(d[O+27]), "=f"(d[O+28]), "=f"(d[O+29]), "=f"(d[O+30]), "=f"(d[O+31]), "=f"(d[O+32]), "=f"(d[O+33]), "=f"(d[O+34]), "=f"(d[O+35]), "=f"(d[O+36]), "=f"(d[O+37]), "=f"(d[O+38]), "=f"(d[O+39]), "=f"(d[O+40]), "=f"(d[O+41]), "=f"(d[O+42]), "=f"(d[O+43]), "=f"(d[O+44]), "=f"(d[O+45]), "=f"(d[O+46]), "=f"(d[O+47]), "=f"(d[O+48]), "=f"(d[O+49]), "=f"(d[O+50]), "=f"(d[O+51]), "=f"(d[O+52]), "=f"(d[O+53]), "=f"(d[O+54]), "=f"(d[O+55]), "=f"(d[O+56]), "=f"(d[O+57]), "=f"(d[O+58]), "=f"(d[O+59]), "=f"(d[O+60]), "=f"(d[O+61]), "=f"(d[O+62]), "=f"(d[O+63])
   : "r"(a0), "r"(a1), "r"(a2), "r"(a3), "l"(db), "n"(TB));
  else asm volatile("{\n.reg .pred p;\nsetp.ne.b32 p, %70, 0;\nwgmma.mma_async.sync.aligned.m64n128k16.f32.bf16.bf16 {%0,%1,%2,%3,%4,%5,%6,%7,%8,%9,%10,%11,%12,%13,%14,%15,%16,%17,%18,%19,%20,%21,%22,%23,%24,%25,%26,%27,%28,%29,%30,%31,%32,%33,%34,%35,%36,%37,%38,%39,%40,%41,%42,%43,%44,%45,%46,%47,%48,%49,%50,%51,%52,%53,%54,%55,%56,%57,%58,%59,%60,%61,%62,%63}, {%64,%65,%66,%67}, %68, p, 1, 1, %69;\n}"
   : "+f"(d[O+0]), "+f"(d[O+1]), "+f"(d[O+2]), "+f"(d[O+3]), "+f"(d[O+4]), "+f"(d[O+5]), "+f"(d[O+6]), "+f"(d[O+7]), "+f"(d[O+8]), "+f"(d[O+9]), "+f"(d[O+10]), "+f"(d[O+11]), "+f"(d[O+12]), "+f"(d[O+13]), "+f"(d[O+14]), "+f"(d[O+15]), "+f"(d[O+16]), "+f"(d[O+17]), "+f"(d[O+18]), "+f"(d[O+19]), "+f"(d[O+20]), "+f"(d[O+21]), "+f"(d[O+22]), "+f"(d[O+23]), "+f"(d[O+24]), "+f"(d[O+25]), "+f"(d[O+26]), "+f"(d[O+27]), "+f"(d[O+28]), "+f"(d[O+29]), "+f"(d[O+30]), "+f"(d[O+31]), "+f"(d[O+32]), "+f"(d[O+33]), "+f"(d[O+34]), "+f"(d[O+35]), "+f"(d[O+36]), "+f"(d[O+37]), "+f"(d[O+38]), "+f"(d[O+39]), "+f"(d[O+40]), "+f"(d[O+41]), "+f"(d[O+42]), "+f"(d[O+43]), "+f"(d[O+44]), "+f"(d[O+45]), "+f"(d[O+46]), "+f"(d[O+47]), "+f"(d[O+48]), "+f"(d[O+49]), "+f"(d[O+50]), "+f"(d[O+51]), "+f"(d[O+52]), "+f"(d[O+53]), "+f"(d[O+54]), "+f"(d[O+55]), "+f"(d[O+56]), "+f"(d[O+57]), "+f"(d[O+58]), "+f"(d[O+59]), "+f"(d[O+60]), "+f"(d[O+61]), "+f"(d[O+62]), "+f"(d[O+63])
   : "r"(a0), "r"(a1), "r"(a2), "r"(a3), "l"(db), "n"(TB), "r"(sd));
}

#define NEARLY 0
#define XAHEAD 3
#define HEADN 6
#define WBATCH 1
#define NOLDS 2
#define NOSEND 0
#define MSPLIT 3
#define PFALL 1
#define SPACE 100
#define WPF 1
#define WAFTER 7
#define WPACE 0
#define GATE_AT 4
#define TPACE 40
#define PFMODE 0
#define MAPMODE 1
template <int V> struct IC { static constexpr int value = V; };
struct Maps { CUtensorMap x, ft, g64, u64, e, wr, wi, xs, ts, t, g32, u32, d224, o; };

constexpr int NCTA = 130;
constexpr int U = 16384;
constexpr int TB = 36864;
constexpr int OFF_RING = 8 * U, OFF_Z = 9 * U, OFF_XB = 12 * U, OFF_T = 13 * U, OFF_D = OFF_T;
constexpr int OFF_BAR = 14 * U, OFF_SP = OFF_BAR + 512, OFF_G = OFF_SP + 1024 + 128;
constexpr int SMEM_BYTES = OFF_G + 512;
constexpr int B_FX = 0, B_FA = 8, B_FT = 12, B_Z = 16, B_W = 24, B_HX = 25, B_TL = 26, B_HP = 27, B_WR = 30, B_E0 = 34;
constexpr int B_EA = 35, B_ET = 39, B_PZ = 43, B_RDY = 45, B_FE = 46;
constexpr int B_T = 50, B_XS = 51, B_G = 53, NBAR = 54;
__host__ __device__ constexpr int rslot(int n) { return n & 3; }
__host__ __device__ constexpr int rpar(int n) { return (n >> 2) & 1; }

__global__ void __cluster_dims__(2, 1, 1) __launch_bounds__(512, 1)
fused_kernel(Work* __restrict__ ws, const uint16_t* __restrict__ dtab, const __nv_bfloat16* __restrict__ w_r, const __nv_bfloat16* __restrict__ w_i,
             const __nv_bfloat16* __restrict__ gate_w, const __grid_constant__ Maps maps) {
  extern __shared__ __align__(1024) uint8_t smem[];
  const uint32_t sb = smem_u32(smem);
  const uint32_t bars = sb + OFF_BAR;
  const int tid = threadIdx.x, lane = tid & 31;
  const int warp = __shfl_sync(0xffffffffu, tid >> 5, 0);
  const bool helper = blockIdx.x >= 128;
  const int cl = (blockIdx.x >> 1) & 63, rank = blockIdx.x & 1;
  const int q4 = (cl & 1) | ((cl >> 2) & 2), rb = ((cl >> 1) & 3) | ((cl >> 4) << 2);
  const int j = 2 * q4 + rank;
  const int f_full = 448 * q4 + (rank ? 256 : 0);
  const int f_half = 448 * q4 + (rank ? 224 : 192);
  const int kg = 2 * j + (rb >> 3), tn = rb & 7;

  if (tid == 64) { PROF_EV(0); PROF_CK(40); }
  if (warp < 8) {
    asm volatile("barrier.cluster.arrive.relaxed.aligned;" ::: "memory");
    asm volatile("setmaxnreg.inc.sync.aligned.u32 192;");
    if (!helper) {
      const int wg = warp >> 2, w = warp & 3, g = lane >> 2;
      const bool elect = (tid & 127) == 0;
      float cX[32], cA[64], cB[64], cC[64], ci[64], ct[64];
      const int zero = blockIdx.x >> 16;
      uint32_t h[56], yf[16];
      const uint32_t d0 = (sb & 0x3FFFF) >> 4;
      const uint32_t dK = d0 | (1u << 16), dN = d0 | (512u << 16);
      const uint32_t dX = dK + wg * 512;
      constexpr uint32_t RING = OFF_RING >> 4;
      auto waitA = [&](int n) { mbar_wait(bars + 8 * (B_FA + rslot(n)), rpar(n)); };
      auto freeA = [&](int n) { mbar_arrive_if(elect, bars + 8 * (B_EA + rslot(n))); };
      auto nop = [] {};

      asm volatile("bar.sync 0, 384;" ::: "memory");
#pragma unroll 1
      for (int i = 0; i < 4; i++) {
        const uint64_t dx = d128(dX + i * 2048), df = d128(dK + (OFF_XB >> 4) + (i & 1) * 1024);
        mbar_wait(bars + 8 * (B_FX + 2 * i), 0);
        wg_fence();
        mma_ss64<0, 0, 2>(cX, df, dx, i);
        mma_ss64<0, 0, 1>(cX, df + 2, dx + 2);
        wg_commit(); wg_wait<1>();
        mbar_arrive_if(elect && i, bars + 8 * (B_EA + rslot(i - 1)));
        mma_ss64<0, 0, 1>(cX, df + 4, dx + 4);
        mma_ss64<0, 0, 1>(cX, df + 6, dx + 6);
        if (i == 0 && tid == 0) PROF_EV(1);
        mbar_wait(bars + 8 * (B_FX + 2 * i + 1), 0);
        wg_fence();
#pragma unroll
        for (int k = 0; k < 4; k++) mma_ss64<0, 0, 1>(cX, df + (512 + k * 2), dx + (1024 + k * 2));
        wg_commit();
        waitA(i);
        wg_fence();
        const uint64_t da = d128(dX + i * 1024), db = d128(dN + RING + i * 1024);
        mma_ss128<0, 1, 2>(cA, da, db, i);
        wg_commit(); wg_wait<1>();
        mbar_arrive_if(elect, bars + 8 * (B_FE + i));
#pragma unroll
        for (int k = 1; k < 4; k++) mma_ss128<0, 1, 1>(cA, da + k * 2, db + k * 128);
        wg_commit();
      }
      fence_regs<0, 32>(cX);
#pragma unroll
      for (int e = 0; e < 16; e++) yf[e] = pack_pin(cX[2 * e], cX[2 * e + 1]);
      if (tid == 0) PROF_EV(2);
      {
        waitA(4); mbar_wait(bars + 8 * B_E0, 0);
        const uint64_t de = d128(dN + (wg ? RING : OFF_XB >> 4));
        wg_fence();
        mma_rs128<0, 1, 0>(cB, yf[0], yf[1], yf[2], yf[3], de);
        wg_commit();
        wg_wait<1>();
        freeA(3);
#pragma unroll
        for (int k = 1; k < 4; k++) mma_rs128<0, 1, 1>(cB, yf[4 * k], yf[4 * k + 1], yf[4 * k + 2], yf[4 * k + 3], de + k * 128);
        wg_commit();
      }
      bool rel = false;
      auto acquire = [&](int n) {
        rel = elect;
        if (!mbar_try(bars + 8 * (B_FA + rslot(n)), rpar(n))) { wg_wait<0>(); freeA(n - 1); rel = false; waitA(n); }
      };
      auto freeP = [&](int n) { mbar_arrive_if(rel, bars + 8 * (B_EA + rslot(n - 1))); };
      auto ffn_step = [&](auto first, auto split, float (&acc)[64], int n, int kb, auto done, auto work) {
        constexpr int SPLIT = decltype(split)::value;
        acquire(n);
        wg_fence();
        const uint64_t dx = d128(dX + kb * 1024), db = d128(dN + RING + rslot(n) * 1024);
        mma_ss128<0, 1, decltype(first)::value>(acc, dx, db, kb);
#pragma unroll
        for (int k = 1; k < SPLIT; k++) mma_ss128<0, 1, 1>(acc, dx + k * 2, db + k * 128);
        wg_commit();
        work();
        wg_wait<1>();
        freeP(n);
        done();
        if (SPLIT < 4) {
          wg_fence();
#pragma unroll
          for (int k = SPLIT; k < 4; k++) mma_ss128<0, 1, 1>(acc, dx + k * 2, db + k * 128);
          wg_commit();
        }
      };
      {
        const int s0 = 2 * rb + wg, kr = 2 * ((s0 & 1) | ((s0 & 4) >> 1));
        const int m = lane >> 3, r = lane & 7;
        const uint32_t a0 = sb + OFF_XB + wg * 8192 + (((w >> 1) * 8 + (m >> 1)) * 2 + (w & 1)) * 256 + (m & 1) * 128 + ((r ^ (kr + (m & 1))) << 4);
        ffn_step(IC<1>(), IC<4>(), cA, 5, 4, [&] { fence_regs<0, 64>(cB); }, nop);
        asm volatile("bar.sync 5, 256;" ::: "memory");
#pragma unroll
        for (int i = 0; i < 4; i++)
          stsm4t(a0 + i * 1024, pack_bf16(cB[8 * i] - cB[34 + 8 * i], cB[8 * i + 1] - cB[35 + 8 * i]),
                 pack_bf16(cB[32 + 8 * i] + cB[8 * i + 2], cB[33 + 8 * i] + cB[8 * i + 3]),
                 pack_bf16(cB[8 * i + 4] - cB[38 + 8 * i], cB[8 * i + 5] - cB[39 + 8 * i]),
                 pack_bf16(cB[36 + 8 * i] + cB[8 * i + 6], cB[37 + 8 * i] + cB[8 * i + 7]));
        if (j == 0 && w == 0) {
          const uint32_t a1 = r ? sb + OFF_SP + 1024 : sb + OFF_SP + wg * 512 + (m & 1) * 256 + (m >> 1) * 128;
#pragma unroll
          for (int n = 0; n < 8; n++)
            asm volatile("stmatrix.sync.aligned.m8n8.x4.shared.b16 [%0], {%1,%2,%3,%4};" ::"r"(a1 + ((n ^ (kr + (m >> 1))) << 4)),
                         "r"(pack_bf16(cB[4 * n], cB[4 * n + 1])), "r"(pack_bf16(cB[4 * n + 2], cB[4 * n + 3])),
                         "r"(pack_bf16(cB[32 + 4 * n], cB[33 + 4 * n])), "r"(pack_bf16(cB[34 + 4 * n], cB[35 + 4 * n])) : "memory");
        }
        ffn_step(IC<1>(), IC<2>(), cA, 6, 5, nop, [&] {
          asm volatile("fence.proxy.async.shared::cta;" ::: "memory");
          __syncwarp();
          mbar_arrive_if(lane == 0, bars + 8 * (B_XS + wg));
          if (tid == 0) PROF_EV(3);
        });
      }
#pragma unroll 1
      for (int kb = 6; kb < 8; kb++) ffn_step(IC<1>(), IC<1>(), cA, 1 + kb, kb, nop, nop);
      float g0 = 0.f, g1 = 0.f;
      uint32_t tag = 0;
      auto glu = [&](auto& acc, int half, int ho, int i0, int i1) {
#pragma unroll
        for (int i = i0; i < i1; i++) {
          const float o = 1.0f - ((i & 1) ? g1 : g0);
          asm volatile("" : "+f"(acc[2 * i]), "+f"(acc[2 * i + 1]), "+f"(acc[half + 2 * i]), "+f"(acc[half + 1 + 2 * i])::"memory");
          h[ho + i] = pack_pin(fmaxf(acc[2 * i], 0.f) * acc[half + 2 * i] * o, fmaxf(acc[2 * i + 1], 0.f) * acc[half + 1 + 2 * i] * o);
        }
      };
      ffn_step(IC<2>(), IC<1>(), cB, 9, zero, nop, nop);
#pragma unroll 1
      for (int kb = 1; kb < 8; kb++)
        ffn_step(IC<1>(), IC<1>(), cB, 9 + kb, kb, nop, [&] {
          if (kb == 4 + wg) {
            mbar_wait(bars + 8 * B_G, 0);
            const uint32_t gb0 = *(const uint32_t*)(smem + OFF_G + (wg * 64 + w * 16 + g) * 4), gb1 = *(const uint32_t*)(smem + OFF_G + (wg * 64 + w * 16 + g + 8) * 4);
            tag = gb0 & 1; g0 = __uint_as_float(gb0 & ~1u); g1 = __uint_as_float(gb1 & ~1u);
            glu(cA, 32, 0, 0, 8);
          } else if (kb == 6 + wg) glu(cA, 32, 0, 8, 16);
        });
      if (tid == 0) PROF_EV(4);
      ffn_step(IC<0>(), IC<1>(), cC, 17, 0, nop, nop);
#pragma unroll 1
      for (int kb = 1; kb < 8; kb++)
        ffn_step(IC<1>(), IC<1>(), cC, 17 + kb, kb, nop, [&] {
          if (kb == 1 + wg) glu(cB, 32, 16, 0, 8);
          else if (kb == 3 + wg) glu(cB, 32, 16, 8, 16);
        });
      if (tid == 0) PROF_EV(5);
      auto m_step = [&](auto first, int i) {
        acquire(25 + i);
        wg_fence();
        const uint64_t dx = d128(dX + i * 2048), dm = d64(dN + RING + rslot(25 + i) * 1024);
        mma_ss64<0, 1, decltype(first)::value>(ct, dx, dm);
#pragma unroll
        for (int k = 1; k < MSPLIT; k++) mma_ss64<0, 1, 1>(ct, dx + ((k >> 2) * 1024 + (k & 3) * 2), dm + k * 64);
        wg_commit();
        wg_wait<1>();
        mbar_arrive_if(rel && i < 3, bars + 8 * (B_EA + rslot(24 + i)));
        mbar_arrive_if(elect && i, bars + 8 * (B_ET + i - 1));
        wg_fence();
#pragma unroll
        for (int k = MSPLIT; k < 8; k++) mma_ss64<0, 1, 1>(ct, dx + ((k >> 2) * 1024 + (k & 3) * 2), dm + k * 64);
        wg_commit();
      };
      auto freeT = [&](int t) { mbar_arrive_if(elect, bars + 8 * (B_ET + t)); };
      m_step(IC<0>(), 0);
#pragma unroll 1
      for (int i = 1; i < 5; i++) {
        if (i == 1 + wg) glu(cC, 32, 32, 0, 8);
        else if (i == 3 + wg) glu(cC, 32, 32, 8, 16);
        if (i < 4) m_step(IC<1>(), i);
      }
      waitA(29 + wg);
      if (tid == 0) PROF_EV(6);
      if (tid == 128) PROF_EV(27);
      mbar_wait(bars + 8 * (j == 0 ? B_T : B_TL), 0);
      if (tid == 0) PROF_EV(7);
      wg_fence();
      {
        const uint64_t dt = d128(dN + (OFF_T >> 4) + wg * 512), de = d128(dK + RING + (1 + wg) * 1024);
        mma_ss64<0, 1, 0>(ci, de, dt);
        mma_ss64<32, 1, 0>(ci, de + 512, dt);
#pragma unroll
        for (int k = 1; k < 4; k++) {
          mma_ss64<0, 1, 1>(ci, de + k * 2, dt + k * 128);
          mma_ss64<32, 1, 1>(ci, de + (512 + k * 2), dt + k * 128);
        }
        wg_commit();
        wg_wait<1>();
        freeT(3);
        fence_regs<0, 32>(ct);
        glu(ct, 16, 48, 0, 8);
      }

      auto twait = [&](uint32_t bar, uint32_t par, int) { mbar_wait(bar, par); };
      const int fo = warp * 128 + lane;
      auto fetch = [&](uint4 (&pv)[4], int z) {
        twait(bars + 8 * (z < 4 ? B_Z + 2 * z + wg : B_HP + z - 4), 0, 8 + z);
        const uint8_t* src = smem + (z < 5 ? OFF_Z + z * U : (z - 5) * U) + fo * 16;
#pragma unroll
        for (int i = 0; i < 4; i++) pv[i] = *(const uint4*)(src + i * 512);
      };
      auto check = [&](uint4 (&pv)[4], int z) {
        const uint32_t t0 = (uint32_t)clock();
        while (__any_sync(0xffffffffu, ((pv[0].x ^ tag) | (pv[1].x ^ tag) | (pv[2].x ^ tag) | (pv[3].x ^ tag)) & 1)) {
#pragma unroll
          for (int i = 0; i < 4; i++) pv[i] = ld_x4(ws->part + (size_t)((rb * 8 + j) * 3 + z - 4) * 1024 + fo + i * 32);
          spin_guard(t0);
        }
#pragma unroll
        for (int i = 0; i < 4; i++) pv[i].x &= ~1u;
      };
      auto head = [&](auto off, int t, bool init) {
        constexpr int O = decltype(off)::value;
        twait(bars + 8 * (B_FT + (t & 3)), t >> 2, t);
        const uint64_t db = d128(dN + (t & 3) * (TB >> 4) + rank * 256);
        wg_fence();
        mma_rs64<O, 1, 2>(ct, h[0], h[1], h[2], h[3], db, zero + init);
#pragma unroll
        for (int k = 1; k < 6; k++) mma_rs64<O, 1, 1>(ct, h[4 * k], h[4 * k + 1], h[4 * k + 2], h[4 * k + 3], db + k * 128);
        wg_commit();
        wg_wait<1>();
      };
      auto rest = [&](auto off, int t, int z) {
        constexpr int O = decltype(off)::value, P = 32 - O;
        const uint64_t db = d128(dN + (t & 3) * (TB >> 4)), dw = db + rank * 256, dm = db + (rank ? 0 : 1536);
        wg_fence();
#pragma unroll
        for (int k = 6; k < 12; k++) mma_rs64<O, 1, 1>(ct, h[4 * k], h[4 * k + 1], h[4 * k + 2], h[4 * k + 3], dw + k * 128);
        wg_commit();
        uint4 pv[4];
        if (z >= 0) fetch(pv, z);
        wg_fence();
#pragma unroll
        for (int k = 0; k < 2; k++) mma_rs64<O, 1, 1>(ct, h[48 + 4 * k], h[49 + 4 * k], h[50 + 4 * k], h[51 + 4 * k], dm + k * 128);
#pragma unroll
        for (int k = 0; k < 4; k++) mma_rs64<O, 1, 1>(ct, yf[4 * k], yf[4 * k + 1], yf[4 * k + 2], yf[4 * k + 3], db + (14 + k) * 128);
        wg_commit();
        if (z >= 0) {
          if (z >= 4) check(pv, z);
#pragma unroll
          for (int i = 0; i < 4; i++) {
            const uint32_t a[4] = {pv[i].x, pv[i].y, pv[i].z, pv[i].w};
#pragma unroll
            for (int e = 0; e < 4; e++) { ct[P + 8 * i + 2 * e] = bf_lo(a[e]); ct[P + 8 * i + 2 * e + 1] = bf_hi(a[e]); }
          }
        }
      };
      const uint32_t peerZ = mapa(sb + OFF_Z + fo * 16, rank ^ 1), peerB = mapa(bars + 8 * (B_Z + wg), rank ^ 1);
      auto send = [&](auto off, int t) {
        constexpr int O = decltype(off)::value;
        fence_regs<O, 32>(ct);
        const bool grid = t >= 3 && t < 6;
        const int z = grid ? t - 3 : t == 6 ? 3 : t;
        uint32_t pk[16];
#pragma unroll
        for (int i = 0; i < 16; i++) pk[i] = pack_bf16(ct[O + 2 * i], ct[O + 2 * i + 1]);
        if (grid) {
          const int owner = rb * 8 + 2 * ((q4 + z + 1) & 3) + rank;
          uint4* dst = ws->part + (size_t)(owner * 3 + z) * 1024 + fo;
#pragma unroll
          for (int i = 0; i < 4; i++) st_x4(dst + i * 32, (pk[4 * i] & ~1u) | tag, pk[4 * i + 1], pk[4 * i + 2], pk[4 * i + 3]);
          __syncwarp();
          hint_add_if(lane == 0, &ws->cntP[32 * owner + z]);
        } else {
#pragma unroll
          for (int i = 0; i < 4; i++)
            asm volatile("st.async.weak.shared::cluster.mbarrier::complete_tx::bytes.v4.b32 [%0], {%1,%2,%3,%4}, [%5];" ::"r"(peerZ + z * U + i * 512),
                         "r"(pk[4 * i]), "r"(pk[4 * i + 1]), "r"(pk[4 * i + 2]), "r"(pk[4 * i + 3]), "r"(peerB + 16 * z) : "memory");
        }
      };
      asm volatile("barrier.cluster.wait.aligned;" ::: "memory");
      head(IC<0>(), 0, false);
      if (elect) asm volatile("mbarrier.arrive.shared::cluster.b64 _, [%0];" ::"r"(mapa(bars + 8 * B_RDY, rank ^ 1)) : "memory");
      mbar_arrive_if(elect, bars + 8 * (B_PZ + 1));
      fence_regs<0, 64>(ci);
#pragma unroll
      for (int i = 0; i < 16; i++) {
        const float gg = ((i & 1) ? g1 : g0) * (2.0f / (2048.0f * 512.0f));
        if (i & 2) yf[i] = pack_pin((ci[2 * i] - ci[28 + 2 * i]) * gg, (ci[2 * i + 1] - ci[29 + 2 * i]) * gg);
        else yf[i] = pack_pin((ci[2 * i] + ci[36 + 2 * i]) * gg, (ci[2 * i + 1] + ci[37 + 2 * i]) * gg);
      }
      if (tid == 0) PROF_EV(8);
      if (tid == 128) PROF_EV(28);
#pragma unroll 1
      for (int t = 0;; t += 2) {
        rest(IC<0>(), t, t - 2);
        head(IC<32>(), t + 1, t >= 2);
        mbar_arrive_if(elect && t < 6, bars + 8 * (B_ET + t));
        if (t == 0) twait(bars + 8 * B_RDY, 0, 15);
        send(IC<0>(), t);
        rest(IC<32>(), t + 1, (t & 2) ? t - 1 : -1);
        if (t == 6) break;
        head(IC<0>(), t + 2, t == 2);
        mbar_arrive_if(elect && t < 4, bars + 8 * (B_ET + t + 1));
        send(IC<32>(), t + 1);
      }
      if (tid == 0) PROF_EV(9);
      if (tid == 128) PROF_EV(29);
      {
        float (&sum)[64] = ct;
        uint4 p2[4], p3[4];
        fetch(p3, 3);
        if (tid == 0) PROF_EV(25);
        fetch(p2, 6);
        if (tid == 0) PROF_EV(24);
        check(p2, 6);
#pragma unroll
        for (int i = 0; i < 4; i++) {
          const uint32_t b[4] = {p2[i].x, p2[i].y, p2[i].z, p2[i].w}, c[4] = {p3[i].x, p3[i].y, p3[i].z, p3[i].w};
#pragma unroll
          for (int e = 0; e < 4; e++) {
            sum[8 * i + 2 * e] += bf_lo(c[e]) + bf_lo(b[e]);
            sum[8 * i + 2 * e + 1] += bf_hi(c[e]) + bf_hi(b[e]);
          }
        }
        if (tid == 0) PROF_EV(14);
        wg_wait<0>();
        fence_regs<32, 32>(ct);
#pragma unroll
        for (int i = 0; i < 32; i++) sum[i] += ct[32 + i];
        const uint32_t stg = sb + OFF_T + warp * 2048;
        const int mr = (lane & 7) + ((lane >> 3) & 1) * 8, mc = lane >> 4;
#pragma unroll
        for (int i = 0; i < 4; i++) {
          const uint32_t a = stg + mr * 128 + (((2 * i + mc) ^ (mr & 7)) << 4);
          asm volatile("stmatrix.sync.aligned.m8n8.x4.shared.b16 [%0], {%1,%2,%3,%4};" ::"r"(a), "r"(pack_bf16(sum[8 * i], sum[8 * i + 1])),
                       "r"(pack_bf16(sum[8 * i + 2], sum[8 * i + 3])), "r"(pack_bf16(sum[8 * i + 4], sum[8 * i + 5])),
                       "r"(pack_bf16(sum[8 * i + 6], sum[8 * i + 7])) : "memory");
        }
        asm volatile("fence.proxy.async.shared::cta;" ::: "memory");
        __syncwarp();
        if (elect_one()) {
          asm volatile("cp.async.bulk.tensor.3d.global.shared::cta.bulk_group [%0, {%2, %3, %4}], [%1];" ::"l"(&maps.o), "r"(stg), "r"(64 * j),
                       "r"(16 * w), "r"(2 * rb + wg) : "memory");
          asm volatile("cp.async.bulk.commit_group;\ncp.async.bulk.wait_group.read 0;" ::: "memory");
        }
      }
      if (tid == 0) { PROF_EV(15); PROF_CK(41); }
      if (tid == 128) PROF_EV(30);
    }
  } else if (warp < 12) {
    asm volatile("setmaxnreg.dec.sync.aligned.u32 104;");
    asm volatile("barrier.cluster.arrive.relaxed.aligned;" ::: "memory");
    const int t = tid - 256, w = warp - 8;
    const uint32_t ep = ld_x1(&ws->epoch[blockIdx.x * 8]);
    const uint32_t tag = (ep + 1) & 1;
    auto w_issue = [&](const CUtensorMap* m) {
          if (elect_one()) { mbar_expect_tx(bars + 8 * (B_WR + w), 3072); tma4d(sb + OFF_T + w * 3072, m, bars + 8 * (B_WR + w), 16 * kg, 0, 2 * w, tn); }
          __syncwarp();
    };
    auto gate_rows = [&] {
      const int r = 16 * j + 4 * w + (lane >> 3);
      const uint4* pg = (const uint4*)gate_w + (lane & 7);
      {
        float a = 0.f;
        asm volatile("bar.sync 4, 256;" ::: "memory");
#pragma unroll 1
        for (int hf = 0; hf < 2; hf++) {
          uint4 v[4], u[4];
#pragma unroll
          for (int kb = 0; kb < 4; kb++) v[kb] = __ldg(pg + (4 * hf + kb) * 8);
          mbar_wait(bars + 8 * (B_FE + 1 + 2 * hf), 0);
          if (hf) w_issue(&maps.wr);
#pragma unroll
          for (int kb = 0; kb < 4; kb++) u[kb] = *(const uint4*)(smem + (4 * hf + kb) * U + r * 128 + (((lane ^ r) & 7) << 4));
#pragma unroll
          for (int kb = 0; kb < 4; kb++) {
            a = fmaf(bf_lo(u[kb].x), bf_lo(v[kb].x), a); a = fmaf(bf_hi(u[kb].x), bf_hi(v[kb].x), a);
            a = fmaf(bf_lo(u[kb].y), bf_lo(v[kb].y), a); a = fmaf(bf_hi(u[kb].y), bf_hi(v[kb].y), a);
            a = fmaf(bf_lo(u[kb].z), bf_lo(v[kb].z), a); a = fmaf(bf_hi(u[kb].z), bf_hi(v[kb].z), a);
            a = fmaf(bf_lo(u[kb].w), bf_lo(v[kb].w), a); a = fmaf(bf_hi(u[kb].w), bf_hi(v[kb].w), a);
          }
        }
#pragma unroll
        for (int o = 4; o; o >>= 1) a += __shfl_xor_sync(0xffffffffu, a, o);
        if ((lane & 7) == 0)
          asm volatile("st.relaxed.gpu.global.f32 [%0], %1;" ::"l"(ws->gate + rb * 128 + r), "f"(tagf(__fdividef(1.0f, 1.0f + __expf(-a)), tag)) : "memory");
        if (t == 0) PROF_EV(18);
      }
    };
    {
      const int g = lane >> 2, q = lane & 3;
      uint32_t wf[32];
      if (!helper) {
        gate_rows();
        const uint32_t wa = sb + OFF_T + w * (3072 + 4) + q * 48 + g * 2;
#pragma unroll 1
        for (int ri = 0; ri < 2; ri++) {
          mbar_wait(bars + 8 * (B_WR + w), ri);
#pragma unroll
          for (int n2 = 0; n2 < NOLDS; n2++) {
            uint32_t v[16];
#pragma unroll
            for (int i = 0; i < 16; i++)
              asm volatile("ld.shared.u16 %0, [%1];" : "=r"(v[i]) : "r"(wa + (4 * n2 + ((i >> 1) & 3)) * 192 + (i & 1) * (1536 + 2) + (i >> 3) * 16) : "memory");
#pragma unroll
            for (int i = 0; i < 16; i++) {
              uint32_t& d = wf[(i >> 3) * 16 + 8 * n2 + (i & 7)];
              d = __byte_perm(d, v[i], 0x5432);
              asm volatile("" : "+r"(d)::"memory");
            }
          }
          __syncwarp();
          if (ri == 0) w_issue(&maps.wi);
        }
        asm volatile("bar.sync 1, 128;" ::: "memory");
        if (t == 0) PROF_EV(11);
      } else {
        asm volatile("bar.sync 4, 256;" ::: "memory");
        hint_wait(&ws->cntW[0], (ep + 1) * 128u);
        const uint32_t t0 = (uint32_t)clock();
#pragma unroll 1
        for (;;) {
          uint32_t bad = 0;
#pragma unroll
          for (int i = 0; i < 32; i++) {
            const float2 v = ld_x2((const float2*)ws->Wh + (i >> 4) * 2048 + 16 * w + g + 8 * (i & 1) + 64 * q + ((i >> 1) & 7) * 256);
            wf[i] = __float_as_uint(v.x); bad |= __float_as_uint(v.y) ^ tag;
          }
          if (!__any_sync(0xffffffffu, bad & 1)) break;
          spin_guard(t0);
        }
        if (t == 0) PROF_EV(11);
      }
      if (w == 0 && elect_one()) { mbar_expect_tx(bars + 8 * B_W, 8192); bulk_load(sb + OFF_D, dtab, 8192, bars + 8 * B_W); }
      if (!helper) {
        const uint32_t t0 = (uint32_t)clock();
        uint32_t v;
        do { v = ld_x1(ws->gate + rb * 128 + t); spin_guard(t0); } while (__any_sync(0xffffffffu, (v ^ tag) & 1));
        *(uint32_t*)(smem + OFF_G + t * 4) = v;
        __syncwarp();
        mbar_arrive_if(lane == 0, bars + 8 * B_G);
      }
      mbar_wait(bars + 8 * B_W, 0);
      mbar_wait(bars + 8 * B_HX, 0);
      if (t == 0) PROF_EV(12);
      const uint32_t dd = (sb & 0x3FFFF) >> 4;
      const uint64_t dF = d128((dd + (OFF_D >> 4)) | (512u << 16)), dI = d128((dd + (OFF_D >> 4)) | (1u << 16)), dA = d128((dd + (OFF_XB >> 4)) | (512u << 16));
      float az[32];
      const int zero = blockIdx.x >> 16;
      uint32_t pf[32];
#pragma unroll
      for (int mt = 0; mt < 2; mt++) {
        wg_fence();
        if (mt == 0) mma_ss64<0, 3, 0>(az, dA, dF);
        else mma_ss64<0, 3, 2>(az, dA + 512, dF, zero);
#pragma unroll
        for (int k = 1; k < 4; k++) mma_ss64<0, 3, 1>(az, dA + (mt * 512 + k * 128), dF + k * 128);
        wg_commit();
        wg_wait<0>();
        fence_regs<0, 32>(az);
#pragma unroll
        for (int i = 0; i < 16; i++) {
          const float wr = bf_lo(wf[16 * mt + i]), wi = bf_hi(wf[16 * mt + i]);
          pf[16 * mt + i] = pack_pin(fmaf(az[2 * i], wr, -az[2 * i + 1] * wi), fmaf(az[2 * i], wi, az[2 * i + 1] * wr));
        }
      }
      if (t == 0) PROF_EV(16);
#pragma unroll
      for (int mt = 0; mt < 2; mt++) {
        wg_fence();
        mma_rs64<0, 0, 2>(az, pf[16 * mt], pf[16 * mt + 1], pf[16 * mt + 2], pf[16 * mt + 3], dI, mt ? (int)helper : zero);
#pragma unroll
        for (int k = 1; k < 4; k++) mma_rs64<0, 0, 1>(az, pf[16 * mt + 4 * k], pf[16 * mt + 4 * k + 1], pf[16 * mt + 4 * k + 2], pf[16 * mt + 4 * k + 3], dI + k * 2);
        wg_commit();
        wg_wait<0>();
        fence_regs<0, 32>(az);
        if (!helper) {
          const int m = lane >> 3, r = lane & 7;
          const int sl = 2 * (m >> 1) + ((r >> 1) & 1) + 4 * (r >> 2);
          const uint32_t a0 = sb + OFF_XB + (2 * w + (m & 1)) * 2048 + sl * 64 + (((mt * 2 + (r & 1)) ^ (sl >> 1)) << 4);
#pragma unroll
          for (int i = 0; i < 4; i++)
            stsm4t(a0 + i * 512, pack_bf16(az[8 * i], az[8 * i + 1]), pack_bf16(az[8 * i + 2], az[8 * i + 3]), pack_bf16(az[8 * i + 4], az[8 * i + 5]),
                   pack_bf16(az[8 * i + 6], az[8 * i + 7]));
        }
      }
      if (helper) {
#pragma unroll
        for (int i = 0; i < 16; i++) {
          const int n = i >> 1, s0 = 8 * (n >> 1) + 2 * (n & 1) + (q & 1) + 4 * (q >> 1);
          if ((n & 1) == (int)(blockIdx.x & 1)) st_u2(ws->Ts + s0 * 64 + 16 * w + g + 8 * (i & 1), pack_bf16(az[2 * i], az[2 * i + 1]), tag);
        }
        __syncwarp();
        hint_add_if(lane == 0, &ws->cntH[0]);
        if (t == 0) { ws->epoch[blockIdx.x * 8] = ep + 1; PROF_EV(13); }
      } else {
        asm volatile("fence.proxy.async.shared::cta;" ::: "memory");
        __syncwarp();
        if (elect_one()) {
          if (t == 0) PROF_EV(17);
          if (SPACE) __nanosleep(SPACE * w);
          asm volatile("cp.async.bulk.tensor.3d.global.shared::cta.bulk_group [%0, {%2, %3, %4}], [%1];" ::"l"(&maps.ts), "r"(sb + OFF_XB + w * 4096),
                       "r"(32 * kg), "r"(0), "r"(8 * tn + 2 * w) : "memory");
          bulk_done_signal(&ws->cntT[32 * j]);
          if (t == 96) PROF_EV(13);
        }
        __syncwarp();
        if (j == 0) {
          hint_wait(&ws->cntH[0], (ep + 1) * 8u);
          const uint32_t t0 = (uint32_t)clock();
          float2 v;
          do { v = ld_x2((const float2*)ws->Ts + 2 * rb * 64 + t); spin_guard(t0); } while (__any_sync(0xffffffffu, (__float_as_uint(v.y) ^ tag) & 1));
          mbar_wait(bars + 8 * B_TL, 0);
          const uint32_t u = __float_as_uint(v.x);
          *(uint16_t*)(smem + OFF_T + t * 128 + ((t & 7) << 4)) = (uint16_t)u;
          *(uint16_t*)(smem + OFF_T + t * 128 + (((t & 7) ^ 1) << 4)) = (uint16_t)(u >> 16);
          asm volatile("fence.proxy.async.shared::cta;" ::: "memory");
          __syncwarp();
          mbar_arrive_if(lane == 0, bars + 8 * B_T);
        }
      }
    }
  } else {
    asm volatile("setmaxnreg.dec.sync.aligned.u32 24;");
    auto xf_load = [&](int q) {
      const uint32_t fb = bars + 8 * (B_FX + q);
      mbar_expect_tx(fb, U + 8192);
      tma3d(sb + q * U, &maps.x, fb, 64 * q, 0, 2 * rb);
      if (q >= 4) mbar_wait(bars + 8 * (B_FE + ((q - 4) >> 1)), 0);
      tma2d(sb + OFF_XB + (q & 3) * 8192, &maps.ft, fb, 64 * q, 64 * j);
    };
    if (elect_one()) {
      if (warp == 14) {
#pragma unroll
        for (int i = 0; i < B_FT; i++) mbar_init(bars + 8 * i, 1);
        asm volatile("fence.mbarrier_init.release.cluster;" ::: "memory");
        if (!helper) {
#pragma unroll 1
          for (int n = 0; n < 2; n++) {
            const uint32_t fb = bars + 8 * (B_FA + n);
            xf_load(2 * n); xf_load(2 * n + 1);
            mbar_expect_tx(fb, U);
            tma2d(sb + OFF_RING + n * U, &maps.g64, fb, f_full, 64 * n);
            tma2d(sb + OFF_RING + n * U + 8192, &maps.u64, fb, f_full, 64 * n);
          }
        }
      } else if (warp == 15) {
#pragma unroll
        for (int i = B_FT; i < NBAR; i++) mbar_init(bars + 8 * i, i < B_EA ? 1 : i < B_T ? 2 : 4);
#pragma unroll
        for (int i = 0; i < 8; i++) mbar_expect_tx(bars + 8 * (B_Z + i), U / 2);
        asm volatile("fence.mbarrier_init.release.cluster;" ::: "memory");
        asm volatile("fence.proxy.async.shared::cta;" ::: "memory");
      } else if (warp == 13) {
#pragma unroll
        for (int i = 1; i < 4; i++) asm volatile("prefetch.tensormap [%0];" ::"l"((const char*)&maps + i * 128) : "memory");
      }
    }
    __syncwarp();
    asm volatile("bar.arrive 0, 384;" ::: "memory");
    asm volatile("bar.arrive 4, 256;" ::: "memory");
    __syncwarp();
    asm volatile("barrier.cluster.arrive.relaxed.aligned;" ::: "memory");
    asm volatile("bar.sync 3, 128;" ::: "memory");
    if (warp == 15 && !helper) {
        mbar_wait(bars + 8 * B_FE, 0);
        const uint32_t tag = (ld_x1(&ws->epoch[blockIdx.x * 8]) + 1) & 1;
        const int c = lane >> 4, jj = 16 * blockIdx.x + (lane & 15), jm = (2048 - jj) & 2047;
        const unsigned short* pr = (const unsigned short*)w_r + 256 * c;
        const unsigned short* pi = (const unsigned short*)w_i + 256 * c;
        const float wr = 0.25f * (bf_lo(__ldg(pr + jj * 257)) + bf_lo(__ldg(pr + jm * 257)));
        const float wi = 0.25f * (bf_lo(__ldg(pi + jj * 257)) - bf_lo(__ldg(pi + jm * 257)));
        st_u2(ws->Wh + c * 2048 + jj, c ? pack_bf16(-wi, wr) : pack_bf16(wr, wi), tag);
        __syncwarp();
        hint_add_if(lane == 0, &ws->cntW[0]);
      }
    if ((!helper || warp == 15) && elect_one()) {
      if (warp < 14) {
        const int p = warp - 12;
#pragma unroll 1
        for (int i = 4 + p; i < 14; i += 2) asm volatile("prefetch.tensormap [%0];" ::"l"((const char*)&maps + i * 128) : "memory");
#pragma unroll 1
        for (int n = 2; n < 31; n++) {
          const bool table = n == 4 || n >= 29;
          const int q = n < 4 ? n : n - 1;
          const CUtensorMap* m = table ? &maps.e : n >= 25 ? &maps.g32 + p : &maps.g64 + p;
          const int c0 = table ? 0 : n >= 25 ? f_half : f_full + 64 * (q >> 3);
          const int c1 = table ? (2 * rb + ((n & 1) ^ 1)) * 128 + 64 * p : n >= 25 ? 128 * (n - 25) : 64 * (q & 7);
          const uint32_t fb = bars + 8 * (B_FA + (n & 3)), dst = sb + OFF_RING + (n & 3) * U + p * 8192;
          if (n < 4) mbar_wait(bars + 8 * (B_FE + n - 2), 0);
          else mbar_wait(bars + 8 * (B_EA + (n & 3)), ((n >> 2) & 1) ^ 1);
          tma2d(dst, m, fb, c0, c1);
          if (p == 0) mbar_expect_tx(fb, U);
        }
      } else if (warp == 15) {
        const unsigned ep1 = ld_x1(&ws->epoch[blockIdx.x * 8]) + 1;
        flag_wait(&ws->cntX[helper ? 0 : 32 * j], ep1 * 16u);
        PROF_EV(22);
        mbar_expect_tx(bars + 8 * B_HX, U);
        bulk_load(sb + OFF_XB, ws->X + (size_t)(helper ? 128 : kg * 8 + tn) * 8192, U, bars + 8 * B_HX);
        if (!helper) {
          flag_wait(&ws->cntT[32 * j], ep1 * 64u);
          PROF_EV(23);
          mbar_expect_tx(bars + 8 * B_TL, U);
          tma3d(sb + OFF_T, &maps.t, bars + 8 * B_TL, 64 * j, 0, 2 * rb);
#pragma unroll 1
          for (int i = 0; i < 3; i++) {
            flag_wait(&ws->cntP[32 * (rb * 8 + j) + i], ep1 * 8u);
            mbar_wait(bars + 8 * (B_PZ + (i == 0)), 0);
            if (i == 2) PROF_EV(26);
            mbar_expect_tx(bars + 8 * (B_HP + i), U);
            bulk_load(sb + (i ? (i - 1) * U : OFF_T), ws->part + (size_t)((rb * 8 + j) * 3 + i) * 1024, U, bars + 8 * (B_HP + i));
          }
          ws->epoch[blockIdx.x * 8] = ep1;
        }
      } else {
#pragma unroll 1
        for (int q = 4; q < 8; q++) xf_load(q);
        mbar_wait(bars + 8 * (B_FE + 2), 0);
        mbar_expect_tx(bars + 8 * B_E0, U);
        tma2d(sb + OFF_XB, &maps.e, bars + 8 * B_E0, 0, 2 * rb * 128);
        tma2d(sb + OFF_XB + 8192, &maps.e, bars + 8 * B_E0, 0, 2 * rb * 128 + 64);
#pragma unroll 1
        for (int h2 = 0; h2 < 2; h2++) {
          const int s0 = 2 * rb + h2, sg = (s0 & ~6) | ((s0 & 2) << 1) | ((s0 & 4) >> 1);
          mbar_wait(bars + 8 * (B_XS + h2), 0);
#pragma unroll 1
          for (int c = 0; c < 2; c++) {
            asm volatile("cp.async.bulk.tensor.4d.global.shared::cta.bulk_group [%0, {%2, %3, %4, %5}], [%1];" ::"l"(&maps.xs),
                         "r"(sb + OFF_XB + h2 * 8192 + c * 4096), "r"(0), "r"(sg), "r"(0), "r"(16 * j + 8 * c) : "memory");
            if (j == 0)
              asm volatile("cp.async.bulk.global.shared::cta.bulk_group [%0], [%1], 256;" ::"l"(ws->X + 128 * 8192 + c * 4096 + sg * 128),
                           "r"(sb + OFF_SP + h2 * 512 + c * 256) : "memory");
            if (SPACE && h2 + c < 2) __nanosleep(SPACE);
          }
        }
        bulk_done_signal(&ws->cntX[32 * j]);
        PROF_EV(20);
        asm volatile("prefetch.tensormap [%0];" ::"l"(&maps.o) : "memory");
#pragma unroll 1
        for (int t = 0; t < 8; t++) {
          const int i = t < 3 ? t + 1 : t < 6 ? t - 2 : 0;
          const int col = 64 * (2 * ((q4 + i) & 3) + ((t < 3 || t == 6) ? 1 - rank : rank));
          const uint32_t fb = bars + 8 * (B_FT + (t & 3)), dst = sb + (t & 3) * TB;
          mbar_wait(bars + 8 * (B_ET + (t == 2 ? 3 : t & 3)), t >> 2);
          mbar_expect_tx(fb, TB);
          tma2d(dst, &maps.d224, fb, col, 224 * j);
          if (t < 2) mbar_wait(bars + 8 * (B_ET + t + 1), 0);
          tma2d(dst + 28672, &maps.ft, fb, col, 64 * j);
        }
      }
    }
  }
}

typedef CUresult (*EncodeFn)(CUtensorMap*, CUtensorMapDataType, cuuint32_t, void*, const cuuint64_t*, const cuuint64_t*, const cuuint32_t*,
                             const cuuint32_t*, CUtensorMapInterleave, CUtensorMapSwizzle, CUtensorMapL2promotion, CUtensorMapFloatOOBfill);

static void encode(EncodeFn f, CUtensorMap* m, const void* base, int rank, const cuuint64_t* dims, const cuuint64_t* strides, const cuuint32_t* box,
                   CUtensorMapSwizzle sw) {
  cuuint32_t es[5] = {1, 1, 1, 1, 1};
  f(m, CU_TENSOR_MAP_DATA_TYPE_BFLOAT16, rank, (void*)base, dims, strides, box, es, CU_TENSOR_MAP_INTERLEAVE_NONE, sw,
    CU_TENSOR_MAP_L2_PROMOTION_L2_128B, CU_TENSOR_MAP_FLOAT_OOB_FILL_NONE);
}

extern "C" void kernel_launch(void* const* d_in, const int* in_sizes, int n_in, void* d_out, int out_size) {
  (void)in_sizes; (void)n_in; (void)out_size;
  const __nv_bfloat16* x = (const __nv_bfloat16*)d_in[0];
  const __nv_bfloat16* w_r = (const __nv_bfloat16*)d_in[1];
  const __nv_bfloat16* w_i = (const __nv_bfloat16*)d_in[2];
  const __nv_bfloat16* Wg = (const __nv_bfloat16*)d_in[4];
  const __nv_bfloat16* Wu = (const __nv_bfloat16*)d_in[5];
  const __nv_bfloat16* Wd = (const __nv_bfloat16*)d_in[6];
  const __nv_bfloat16* gw = (const __nv_bfloat16*)d_in[7];

  void* fp = nullptr; cudaDriverEntryPointQueryResult qr;
  cudaGetDriverEntryPoint("cuTensorMapEncodeTiled", &fp, cudaEnableDefault, &qr);
  EncodeFn enc = (EncodeFn)fp;
  void *pFT, *pET, *pDT, *pW;
  cudaGetSymbolAddress(&pDT, g_DT); cudaGetSymbolAddress(&pW, g_work);
  void *pX = ((Work*)pW)->X, *pT = ((Work*)pW)->T;
  cudaGetSymbolAddress(&pFT, g_FT); cudaGetSymbolAddress(&pET, g_ET);

  Maps mp;
  const CUtensorMapSwizzle S128 = CU_TENSOR_MAP_SWIZZLE_128B, S64 = CU_TENSOR_MAP_SWIZZLE_64B;
  { cuuint64_t d[3] = {512, 64, 32}, s[2] = {32768, 1024}; cuuint32_t b[3] = {64, 64, 2}, b2[3] = {64, 16, 1};
    encode(enc, &mp.x, x, 3, d, s, b, S128); encode(enc, &mp.o, d_out, 3, d, s, b2, S128); }
  { cuuint64_t d[2] = {512, 512}, s[1] = {1024}; cuuint32_t b[2] = {64, 64}; encode(enc, &mp.ft, pFT, 2, d, s, b, S128); }
  { cuuint64_t d[4] = {128, 32, 2, 129}, s[3] = {256, 8192, 16384}; cuuint32_t b[4] = {128, 1, 2, 8}; encode(enc, &mp.xs, pX, 4, d, s, b, CU_TENSOR_MAP_SWIZZLE_NONE); }
  { cuuint64_t d[3] = {512, 32, 64}, s[2] = {65536, 1024}; cuuint32_t b[3] = {32, 32, 2}; encode(enc, &mp.ts, pT, 3, d, s, b, S64); }
  { cuuint64_t d[3] = {512, 64, 32}, s[2] = {1024, 65536}; cuuint32_t b[3] = {64, 64, 2}; encode(enc, &mp.t, pT, 3, d, s, b, S128); }
  { cuuint64_t d[2] = {64, 4096}, s[1] = {128}; cuuint32_t b[2] = {64, 64}; encode(enc, &mp.e, pET, 2, d, s, b, S128); }
  { cuuint64_t d[2] = {1792, 512}, s[1] = {3584}; cuuint32_t b[2] = {64, 64}, b2[2] = {32, 128};
    encode(enc, &mp.g64, Wg, 2, d, s, b, S128); encode(enc, &mp.u64, Wu, 2, d, s, b, S128);
    encode(enc, &mp.g32, Wg, 2, d, s, b2, S64); encode(enc, &mp.u32, Wu, 2, d, s, b2, S64); }
  { cuuint64_t d[2] = {512, 1792}, s[1] = {1024}; cuuint32_t b[2] = {64, 224}; encode(enc, &mp.d224, Wd, 2, d, s, b, S128); }
  { cuuint64_t d[4] = {264, 32, 8, 8}, s[3] = {32896, 512, 4112}; cuuint32_t b[4] = {24, 32, 2, 1};
    encode(enc, &mp.wr, w_r, 4, d, s, b, CU_TENSOR_MAP_SWIZZLE_NONE); encode(enc, &mp.wi, w_i, 4, d, s, b, CU_TENSOR_MAP_SWIZZLE_NONE); }

  cudaFuncSetAttribute(fused_kernel, cudaFuncAttributeMaxDynamicSharedMemorySize, SMEM_BYTES);
  fused_kernel<<<NCTA, 512, SMEM_BYTES>>>((Work*)pW, (const uint16_t*)pDT, w_r, w_i, gw, mp);
}
```

```cpp
#include <cuda_runtime.h>
#include <cuda_bf16.h>
#include <cuda.h>
#include <stdint.h>

namespace tbl {
constexpr double PI = 3.14159265358979323846264338327950288;
constexpr double sin_s(double x) { double t = x, s = x; for (int n = 1; n < 12; n++) { t *= -x * x / ((2 * n) * (2 * n + 1)); s += t; } return s; }
constexpr double cos_s(double x) { double t = 1, s = 1; for (int n = 1; n < 12; n++) { t *= -x * x / ((2 * n - 1) * (2 * n)); s += t; } return s; }
constexpr double cos2048(int m) {
  m &= 2047; if (m > 1024) m = 2048 - m;
  bool neg = false; if (m > 512) { m = 1024 - m; neg = true; }
  double v = (m <= 256) ? cos_s(2 * PI * m / 2048) : sin_s(2 * PI * (512 - m) / 2048);
  return neg ? -v : v;
}
constexpr uint16_t to_bf16(double v) {
  if (v == 0) return 0;
  uint16_t s = 0; if (v < 0) { s = 0x8000; v = -v; }
  int e = 0; while (v >= 2) { v /= 2; e++; } while (v < 1) { v *= 2; e--; }
  double m = (v - 1) * 128; int mi = (int)m; double fr = m - mi;
  if (fr > 0.5 || (fr == 0.5 && (mi & 1))) mi++;
  if (mi == 128) { mi = 0; e++; }
  return (uint16_t)(s | ((e + 127) << 7) | mi);
}
struct CosT { uint16_t v[2048]; constexpr CosT() : v() { for (int i = 0; i < 2048; i++) v[i] = to_bf16(cos2048(i)); } };
struct alignas(1024) FT {
  uint16_t v[512 * 512];
  constexpr FT() : v() {
    CosT c;
    for (int r = 0; r < 512; r++) {
      int k = (r >> 4) * 8 + (r & 7), e = (r >> 3) & 1;
      int mul = 4 * k, add = e ? 512 : 0;
      if (k == 0 && e == 1) { mul = 1024; add = 0; }
      for (int d = 0; d < 512; d++) v[r * 512 + d] = c.v[(d * mul + add) & 2047];
    }
  }
};
struct alignas(1024) ET {
  uint16_t v[2048 * 128];
  constexpr ET() : v() {
    CosT c;
    for (int s = 0; s < 2048; s++)
      for (int j = 0; j < 64; j++) {
        const int o = (s & 31) * 8192 + (s >> 5) * 64 + j;
        v[o] = c.v[(s * j) & 2047]; v[o + 4096] = c.v[(s * j + 512) & 2047];
      }
  }
};
struct alignas(1024) DT {
  uint16_t v[64 * 64];
  constexpr DT() : v() {
    CosT c;
    for (int r = 0; r < 64; r++)
      for (int n = 0; n < 64; n++) {
        const int sg = r >> 1, s0 = (sg & ~6) | ((sg & 2) << 1) | ((sg & 4) >> 1), e = r & 1, f = n & 1;
        const int m = 64 * s0 * (n >> 1) + (e == f ? 0 : e ? -512 : 512);
        v[r * 64 + (((n >> 3) ^ (r & 7)) << 3) + (n & 7)] = c.v[m & 2047];
      }
  }
};
}

__device__ constexpr tbl::FT g_FT = tbl::FT();
__device__ constexpr tbl::ET g_ET = tbl::ET();
__device__ constexpr tbl::DT g_DT = tbl::DT();

struct alignas(1024) Work {
  unsigned epoch[132 * 8];
  unsigned cntX[8 * 32], cntT[8 * 32], cntP[128 * 32], cntW[32], cntH[32];
  alignas(16) float gate[16 * 128];
  alignas(16) uint2 Wh[2 * 2048];
  alignas(16) uint2 Ts[32 * 64];
  alignas(1024) uint16_t X[129 * 8192];
  alignas(1024) uint16_t T[32 * 64 * 512];
  alignas(1024) uint4 part[128 * 3 * 1024];
};
__device__ Work g_work;
#define PROF_EV(i) do {} while (0)
#define PROF_CK(i) do {} while (0)

__device__ __forceinline__ uint32_t smem_u32(const void* p) { return (uint32_t)__cvta_generic_to_shared(p); }
__device__ __forceinline__ void mbar_init(uint32_t bar, uint32_t cnt) { asm volatile("mbarrier.init.shared::cta.b64 [%0], %1;" ::"r"(bar), "r"(cnt)); }
__device__ __forceinline__ void mbar_expect_tx(uint32_t bar, uint32_t bytes) { asm volatile("mbarrier.arrive.expect_tx.shared::cta.b64 _, [%0], %1;" ::"r"(bar), "r"(bytes) : "memory"); }
__device__ __forceinline__ void mbar_arrive(uint32_t bar) { asm volatile("mbarrier.arrive.shared::cta.b64 _, [%0];" ::"r"(bar) : "memory"); }
__device__ __forceinline__ bool elect_one() {
  uint32_t p;
  asm volatile("{\n.reg .pred p;\nelect.sync _|p, 0xffffffff;\nselp.u32 %0, 1, 0, p;\n}" : "=r"(p));
  return p;
}
__device__ __forceinline__ void mbar_arrive_if(bool p, uint32_t bar) {
  asm volatile("{\n.reg .pred p;\nsetp.ne.b32 p, %1, 0;\n@p mbarrier.arrive.shared::cta.b64 _, [%0];\n}" ::"r"(bar), "r"((int)p) : "memory");
}
__device__ __forceinline__ void hint_add_if(bool p, unsigned* a) {
  asm volatile("{\n.reg .pred p;\nsetp.ne.b32 p, %1, 0;\n@p red.relaxed.gpu.global.add.u32 [%0], 1;\n}" ::"l"(a), "r"((int)p) : "memory");
}
__device__ __forceinline__ bool mbar_try(uint32_t bar, uint32_t parity) {
  uint32_t ok;
  asm volatile("{\n.reg .pred p;\nmbarrier.test_wait.parity.shared::cta.b64 p, [%1], %2;\nselp.u32 %0, 1, 0, p;\n}" : "=r"(ok) : "r"(bar), "r"(parity) : "memory");
  return ok;
}
__device__ __forceinline__ void mbar_wait(uint32_t bar, uint32_t parity) {
  asm volatile(
      "{\n.reg .pred p;\n.reg .u32 n;\nmov.u32 n, 0;\n"
      "W_LOOP:\nmbarrier.try_wait.parity.shared::cta.b64 p, [%0], %1;\n@p bra W_DONE;\n"
      "add.u32 n, n, 1;\nsetp.lt.u32 p, n, 0x40000;\n@p bra W_LOOP;\ntrap;\nW_DONE:\n}" ::"r"(bar), "r"(parity) : "memory");
}
__device__ __forceinline__ void bulk_load(uint32_t dst, const void* src, uint32_t bytes, uint32_t bar) {
  asm volatile("cp.async.bulk.shared::cluster.global.mbarrier::complete_tx::bytes [%0], [%1], %2, [%3];" ::"r"(dst), "l"(src), "r"(bytes), "r"(bar) : "memory");
}
__device__ __forceinline__ void cp16(uint32_t dst, const void* src) { asm volatile("cp.async.cg.shared.global [%0], [%1], 16;" ::"r"(dst), "l"(src) : "memory"); }
__device__ __forceinline__ void spin_guard(uint32_t t0) { if ((uint32_t)clock() - t0 > (1u << 30)) __trap(); }
__device__ __forceinline__ float tagf(float v, uint32_t tag) { return __uint_as_float((__float_as_uint(v) & ~1u) | tag); }
__device__ __forceinline__ float untag(float v) { return __uint_as_float(__float_as_uint(v) & ~1u); }
__device__ __forceinline__ void st_x2(float2* p, float a, float b) { asm volatile("st.relaxed.gpu.global.v2.f32 [%0], {%1,%2};" ::"l"(p), "f"(a), "f"(b) : "memory"); }
__device__ __forceinline__ float2 ld_x2(const float2* p) { float2 v; asm volatile("ld.relaxed.gpu.global.v2.f32 {%0,%1}, [%2];" : "=f"(v.x), "=f"(v.y) : "l"(p) : "memory"); return v; }
__device__ __forceinline__ void st_u2(uint2* p, uint32_t a, uint32_t b) { asm volatile("st.relaxed.gpu.global.v2.u32 [%0], {%1,%2};" ::"l"(p), "r"(a), "r"(b) : "memory"); }
__device__ __forceinline__ void prefetch2d(const CUtensorMap* m, int c0, int c1) { asm volatile("cp.async.bulk.prefetch.tensor.2d.L2.global [%0, {%1, %2}];" ::"l"(m), "r"(c0), "r"(c1) : "memory"); }
__device__ __forceinline__ void prefetch1d(const void* p, uint32_t bytes) { asm volatile("cp.async.bulk.prefetch.L2.global [%0], %1;" ::"l"(p), "r"(bytes) : "memory"); }
__device__ __forceinline__ uint32_t ld_x1(const void* p) { uint32_t v; asm volatile("ld.relaxed.gpu.global.u32 %0, [%1];" : "=r"(v) : "l"(p) : "memory"); return v; }
__device__ __forceinline__ uint4 ld_x4(const void* p) { uint4 v; asm volatile("ld.relaxed.gpu.global.v4.u32 {%0,%1,%2,%3}, [%4];" : "=r"(v.x), "=r"(v.y), "=r"(v.z), "=r"(v.w) : "l"(p) : "memory"); return v; }
__device__ __forceinline__ void st_x4(void* p, uint32_t a, uint32_t b, uint32_t c, uint32_t d) { asm volatile("st.relaxed.gpu.global.v4.u32 [%0], {%1,%2,%3,%4};" ::"l"(p), "r"(a), "r"(b), "r"(c), "r"(d) : "memory"); }
__device__ __forceinline__ uint32_t mapa(uint32_t a, uint32_t cta) { uint32_t r; asm volatile("mapa.shared::cluster.u32 %0, %1, %2;" : "=r"(r) : "r"(a), "r"(cta)); return r; }
__device__ __forceinline__ void stsm4t(uint32_t a, uint32_t r0, uint32_t r1, uint32_t r2, uint32_t r3) {
  asm volatile("stmatrix.sync.aligned.m8n8.x4.trans.shared.b16 [%0], {%1,%2,%3,%4};" ::"r"(a), "r"(r0), "r"(r1), "r"(r2), "r"(r3) : "memory");
}
__device__ __forceinline__ void hint_add(unsigned* p) { asm volatile("red.relaxed.gpu.global.add.u32 [%0], 1;" ::"l"(p) : "memory"); }
__device__ __forceinline__ void hint_wait(const unsigned* p, unsigned target) {
  const uint32_t t0 = (uint32_t)clock();
  while ((int)(ld_x1(p) - target) < 0) spin_guard(t0);
}
__device__ __forceinline__ void bulk_done_signal(unsigned* p) {
  asm volatile("cp.async.bulk.commit_group;\ncp.async.bulk.wait_group 0;\nfence.proxy.async.global;" ::: "memory");
  hint_add(p);
}
__device__ __forceinline__ void flag_wait(const unsigned* p, unsigned target) {
  hint_wait(p, target);
  asm volatile("fence.proxy.async.global;" ::: "memory");
}
__device__ __forceinline__ void tma2d(uint32_t dst, const CUtensorMap* m, uint32_t bar, int c0, int c1) {
  asm volatile("cp.async.bulk.tensor.2d.shared::cluster.global.mbarrier::complete_tx::bytes [%0], [%1, {%3, %4}], [%2];" ::"r"(dst), "l"(m), "r"(bar), "r"(c0), "r"(c1) : "memory");
}
__device__ __forceinline__ void tma3d(uint32_t dst, const CUtensorMap* m, uint32_t bar, int c0, int c1, int c2) {
  asm volatile("cp.async.bulk.tensor.3d.shared::cluster.global.mbarrier::complete_tx::bytes [%0], [%1, {%3, %4, %5}], [%2];" ::"r"(dst), "l"(m), "r"(bar), "r"(c0), "r"(c1), "r"(c2) : "memory");
}
__device__ __forceinline__ void tma4d(uint32_t dst, const CUtensorMap* m, uint32_t bar, int c0, int c1, int c2, int c3) {
  asm volatile("cp.async.bulk.tensor.4d.shared::cluster.global.mbarrier::complete_tx::bytes [%0], [%1, {%3, %4, %5, %6}], [%2];" ::"r"(dst), "l"(m), "r"(bar), "r"(c0), "r"(c1), "r"(c2), "r"(c3) : "memory");
}
__device__ __forceinline__ void wg_fence() { asm volatile("wgmma.fence.sync.aligned;" ::: "memory"); }
__device__ __forceinline__ void wg_commit() { asm volatile("wgmma.commit_group.sync.aligned;" ::: "memory"); }
template <int N> __device__ __forceinline__ void wg_wait() { asm volatile("wgmma.wait_group.sync.aligned %0;" ::"n"(N) : "memory"); }
template <int O, int N, int NN> __device__ __forceinline__ void fence_regs(float (&d)[NN]) {
#pragma unroll
  for (int i = 0; i < N; i++) asm volatile("" : "+f"(d[O + i])::"memory");
}
__device__ __forceinline__ uint32_t pack_bf16(float lo, float hi) {
  uint32_t r; asm("cvt.rn.bf16x2.f32 %0, %1, %2;" : "=r"(r) : "f"(hi), "f"(lo)); return r;
}
__device__ __forceinline__ uint32_t pack_pin(float lo, float hi) {
  uint32_t r; asm volatile("cvt.rn.bf16x2.f32 %0, %1, %2;" : "=r"(r) : "f"(hi), "f"(lo) : "memory"); return r;
}
__device__ __forceinline__ float bf_lo(uint32_t u) { return __uint_as_float(u << 16); }
__device__ __forceinline__ float bf_hi(uint32_t u) { return __uint_as_float(u & 0xffff0000u); }

__device__ __forceinline__ uint64_t d128(uint32_t lo) { uint64_t d; asm("mov.b64 %0, {%1, 0x40000040};" : "=l"(d) : "r"(lo)); return d; }
__device__ __forceinline__ uint64_t d64(uint32_t lo) { uint64_t d; asm("mov.b64 %0, {%1, 0x80000020};" : "=l"(d) : "r"(lo)); return d; }
template<int O,int TB,int ACC,int NN> __device__ __forceinline__ void mma_ss64(float (&d)[NN], uint64_t da, uint64_t db, int sd = 0){
  if constexpr (ACC == 1) asm volatile("wgmma.mma_async.sync.aligned.m64n64k16.f32.bf16.bf16 {%0,%1,%2,%3,%4,%5,%6,%7,%8,%9,%10,%11,%12,%13,%14,%15,%16,%17,%18,%19,%20,%21,%22,%23,%24,%25,%26,%27,%28,%29,%30,%31}, %32, %33, 1, 1, 1, %35, %34;"
   : "+f"(d[O+0]), "+f"(d[O+1]), "+f"(d[O+2]), "+f"(d[O+3]), "+f"(d[O+4]), "+f"(d[O+5]), "+f"(d[O+6]), "+f"(d[O+7]), "+f"(d[O+8]), "+f"(d[O+9]), "+f"(d[O+10]), "+f"(d[O+11]), "+f"(d[O+12]), "+f"(d[O+13]), "+f"(d[O+14]), "+f"(d[O+15]), "+f"(d[O+16]), "+f"(d[O+17]), "+f"(d[O+18]), "+f"(d[O+19]), "+f"(d[O+20]), "+f"(d[O+21]), "+f"(d[O+22]), "+f"(d[O+23]), "+f"(d[O+24]), "+f"(d[O+25]), "+f"(d[O+26]), "+f"(d[O+27]), "+f"(d[O+28]), "+f"(d[O+29]), "+f"(d[O+30]), "+f"(d[O+31])
   : "l"(da), "l"(db), "n"(TB & 1), "n"(TB >> 1));
  else if constexpr (ACC == 0) asm volatile("wgmma.mma_async.sync.aligned.m64n64k16.f32.bf16.bf16 {%0,%1,%2,%3,%4,%5,%6,%7,%8,%9,%10,%11,%12,%13,%14,%15,%16,%17,%18,%19,%20,%21,%22,%23,%24,%25,%26,%27,%28,%29,%30,%31}, %32, %33, 0, 1, 1, %35, %34;"
   : "=f"(d[O+0]), "=f"(d[O+1]), "=f"(d[O+2]), "=f"(d[O+3]), "=f"(d[O+4]), "=f"(d[O+5]), "=f"(d[O+6]), "=f"(d[O+7]), "=f"(d[O+8]), "=f"(d[O+9]), "=f"(d[O+10]), "=f"(d[O+11]), "=f"(d[O+12]), "=f"(d[O+13]), "=f"(d[O+14]), "=f"(d[O+15]), "=f"(d[O+16]), "=f"(d[O+17]), "=f"(d[O+18]), "=f"(d[O+19]), "=f"(d[O+20]), "=f"(d[O+21]), "=f"(d[O+22]), "=f"(d[O+23]), "=f"(d[O+24]), "=f"(d[O+25]), "=f"(d[O+26]), "=f"(d[O+27]), "=f"(d[O+28]), "=f"(d[O+29]), "=f"(d[O+30]), "=f"(d[O+31])
   : "l"(da), "l"(db), "n"(TB & 1), "n"(TB >> 1));
  else asm volatile("{\n.reg .pred p;\nsetp.ne.b32 p, %36, 0;\nwgmma.mma_async.sync.aligned.m64n64k16.f32.bf16.bf16 {%0,%1,%2,%3,%4,%5,%6,%7,%8,%9,%10,%11,%12,%13,%14,%15,%16,%17,%18,%19,%20,%21,%22,%23,%24,%25,%26,%27,%28,%29,%30,%31}, %32, %33, p, 1, 1, %35, %34;\n}"
   : "+f"(d[O+0]), "+f"(d[O+1]), "+f"(d[O+2]), "+f"(d[O+3]), "+f"(d[O+4]), "+f"(d[O+5]), "+f"(d[O+6]), "+f"(d[O+7]), "+f"(d[O+8]), "+f"(d[O+9]), "+f"(d[O+10]), "+f"(d[O+11]), "+f"(d[O+12]), "+f"(d[O+13]), "+f"(d[O+14]), "+f"(d[O+15]), "+f"(d[O+16]), "+f"(d[O+17]), "+f"(d[O+18]), "+f"(d[O+19]), "+f"(d[O+20]), "+f"(d[O+21]), "+f"(d[O+22]), "+f"(d[O+23]), "+f"(d[O+24]), "+f"(d[O+25]), "+f"(d[O+26]), "+f"(d[O+27]), "+f"(d[O+28]), "+f"(d[O+29]), "+f"(d[O+30]), "+f"(d[O+31])
   : "l"(da), "l"(db), "n"(TB & 1), "n"(TB >> 1), "r"(sd));
}
template<int O,int TB,int ACC,int NN> __device__ __forceinline__ void mma_rs64(float (&d)[NN], uint32_t a0, uint32_t a1, uint32_t a2, uint32_t a3, uint64_t db, int sd = 0){
  if constexpr (ACC == 1) asm volatile("wgmma.mma_async.sync.aligned.m64n64k16.f32.bf16.bf16 {%0,%1,%2,%3,%4,%5,%6,%7,%8,%9,%10,%11,%12,%13,%14,%15,%16,%17,%18,%19,%20,%21,%22,%23,%24,%25,%26,%27,%28,%29,%30,%31}, {%32,%33,%34,%35}, %36, 1, 1, 1, %37;"
   : "+f"(d[O+0]), "+f"(d[O+1]), "+f"(d[O+2]), "+f"(d[O+3]), "+f"(d[O+4]), "+f"(d[O+5]), "+f"(d[O+6]), "+f"(d[O+7]), "+f"(d[O+8]), "+f"(d[O+9]), "+f"(d[O+10]), "+f"(d[O+11]), "+f"(d[O+12]), "+f"(d[O+13]), "+f"(d[O+14]), "+f"(d[O+15]), "+f"(d[O+16]), "+f"(d[O+17]), "+f"(d[O+18]), "+f"(d[O+19]), "+f"(d[O+20]), "+f"(d[O+21]), "+f"(d[O+22]), "+f"(d[O+23]), "+f"(d[O+24]), "+f"(d[O+25]), "+f"(d[O+26]), "+f"(d[O+27]), "+f"(d[O+28]), "+f"(d[O+29]), "+f"(d[O+30]), "+f"(d[O+31])
   : "r"(a0), "r"(a1), "r"(a2), "r"(a3), "l"(db), "n"(TB));
  else if constexpr (ACC == 0) asm volatile("wgmma.mma_async.sync.aligned.m64n64k16.f32.bf16.bf16 {%0,%1,%2,%3,%4,%5,%6,%7,%8,%9,%10,%11,%12,%13,%14,%15,%16,%17,%18,%19,%20,%21,%22,%23,%24,%25,%26,%27,%28,%29,%30,%31}, {%32,%33,%34,%35}, %36, 0, 1, 1, %37;"
   : "=f"(d[O+0]), "=f"(d[O+1]), "=f"(d[O+2]), "=f"(d[O+3]), "=f"(d[O+4]), "=f"(d[O+5]), "=f"(d[O+6]), "=f"(d[O+7]), "=f"(d[O+8]), "=f"(d[O+9]), "=f"(d[O+10]), "=f"(d[O+11]), "=f"(d[O+12]), "=f"(d[O+13]), "=f"(d[O+14]), "=f"(d[O+15]), "=f"(d[O+16]), "=f"(d[O+17]), "=f"(d[O+18]), "=f"(d[O+19]), "=f"(d[O+20]), "=f"(d[O+21]), "=f"(d[O+22]), "=f"(d[O+23]), "=f"(d[O+24]), "=f"(d[O+25]), "=f"(d[O+26]), "=f"(d[O+27]), "=f"(d[O+28]), "=f"(d[O+29]), "=f"(d[O+30]), "=f"(d[O+31])
   : "r"(a0), "r"(a1), "r"(a2), "r"(a3), "l"(db), "n"(TB));
  else asm volatile("{\n.reg .pred p;\nsetp.ne.b32 p, %38, 0;\nwgmma.mma_async.sync.aligned.m64n64k16.f32.bf16.bf16 {%0,%1,%2,%3,%4,%5,%6,%7,%8,%9,%10,%11,%12,%13,%14,%15,%16,%17,%18,%19,%20,%21,%22,%23,%24,%25,%26,%27,%28,%29,%30,%31}, {%32,%33,%34,%35}, %36, p, 1, 1, %37;\n}"
   : "+f"(d[O+0]), "+f"(d[O+1]), "+f"(d[O+2]), "+f"(d[O+3]), "+f"(d[O+4]), "+f"(d[O+5]), "+f"(d[O+6]), "+f"(d[O+7]), "+f"(d[O+8]), "+f"(d[O+9]), "+f"(d[O+10]), "+f"(d[O+11]), "+f"(d[O+12]), "+f"(d[O+13]), "+f"(d[O+14]), "+f"(d[O+15]), "+f"(d[O+16]), "+f"(d[O+17]), "+f"(d[O+18]), "+f"(d[O+19]), "+f"(d[O+20]), "+f"(d[O+21]), "+f"(d[O+22]), "+f"(d[O+23]), "+f"(d[O+24]), "+f"(d[O+25]), "+f"(d[O+26]), "+f"(d[O+27]), "+f"(d[O+28]), "+f"(d[O+29]), "+f"(d[O+30]), "+f"(d[O+31])
   : "r"(a0), "r"(a1), "r"(a2), "r"(a3), "l"(db), "n"(TB), "r"(sd));
}
template<int O,int TB,int ACC,int NN> __device__ __forceinline__ void mma_ss128(float (&d)[NN], uint64_t da, uint64_t db, int sd = 0){
  if constexpr (ACC == 1) asm volatile("wgmma.mma_async.sync.aligned.m64n128k16.f32.bf16.bf16 {%0,%1,%2,%3,%4,%5,%6,%7,%8,%9,%10,%11,%12,%13,%14,%15,%16,%17,%18,%19,%20,%21,%22,%23,%24,%25,%26,%27,%28,%29,%30,%31,%32,%33,%34,%35,%36,%37,%38,%39,%40,%41,%42,%43,%44,%45,%46,%47,%48,%49,%50,%51,%52,%53,%54,%55,%56,%57,%58,%59,%60,%61,%62,%63}, %64, %65, 1, 1, 1, %67, %66;"
   : "+f"(d[O+0]), "+f"(d[O+1]), "+f"(d[O+2]), "+f"(d[O+3]), "+f"(d[O+4]), "+f"(d[O+5]), "+f"(d[O+6]), "+f"(d[O+7]), "+f"(d[O+8]), "+f"(d[O+9]), "+f"(d[O+10]), "+f"(d[O+11]), "+f"(d[O+12]), "+f"(d[O+13]), "+f"(d[O+14]), "+f"(d[O+15]), "+f"(d[O+16]), "+f"(d[O+17]), "+f"(d[O+18]), "+f"(d[O+19]), "+f"(d[O+20]), "+f"(d[O+21]), "+f"(d[O+22]), "+f"(d[O+23]), "+f"(d[O+24]), "+f"(d[O+25]), "+f"(d[O+26]), "+f"(d[O+27]), "+f"(d[O+28]), "+f"(d[O+29]), "+f"(d[O+30]), "+f"(d[O+31]), "+f"(d[O+32]), "+f"(d[O+33]), "+f"(d[O+34]), "+f"(d[O+35]), "+f"(d[O+36]), "+f"(d[O+37]), "+f"(d[O+38]), "+f"(d[O+39]), "+f"(d[O+40]), "+f"(d[O+41]), "+f"(d[O+42]), "+f"(d[O+43]), "+f"(d[O+44]), "+f"(d[O+45]), "+f"(d[O+46]), "+f"(d[O+47]), "+f"(d[O+48]), "+f"(d[O+49]), "+f"(d[O+50]), "+f"(d[O+51]), "+f"(d[O+52]), "+f"(d[O+53]), "+f"(d[O+54]), "+f"(d[O+55]), "+f"(d[O+56]), "+f"(d[O+57]), "+f"(d[O+58]), "+f"(d[O+59]), "+f"(d[O+60]), "+f"(d[O+61]), "+f"(d[O+62]), "+f"(d[O+63])
   : "l"(da), "l"(db), "n"(TB & 1), "n"(TB >> 1));
  else if constexpr (ACC == 0) asm volatile("wgmma.mma_async.sync.aligned.m64n128k16.f32.bf16.bf16 {%0,%1,%2,%3,%4,%5,%6,%7,%8,%9,%10,%11,%12,%13,%14,%15,%16,%17,%18,%19,%20,%21,%22,%23,%24,%25,%26,%27,%28,%29,%30,%31,%32,%33,%34,%35,%36,%37,%38,%39,%40,%41,%42,%43,%44,%45,%46,%47,%48,%49,%50,%51,%52,%53,%54,%55,%56,%57,%58,%59,%60,%61,%62,%63}, %64, %65, 0, 1, 1, %67, %66;"
   : "=f"(d[O+0]), "=f"(d[O+1]), "=f"(d[O+2]), "=f"(d[O+3]), "=f"(d[O+4]), "=f"(d[O+5]), "=f"(d[O+6]), "=f"(d[O+7]), "=f"(d[O+8]), "=f"(d[O+9]), "=f"(d[O+10]), "=f"(d[O+11]), "=f"(d[O+12]), "=f"(d[O+13]), "=f"(d[O+14]), "=f"(d[O+15]), "=f"(d[O+16]), "=f"(d[O+17]), "=f"(d[O+18]), "=f"(d[O+19]), "=f"(d[O+20]), "=f"(d[O+21]), "=f"(d[O+22]), "=f"(d[O+23]), "=f"(d[O+24]), "=f"(d[O+25]), "=f"(d[O+26]), "=f"(d[O+27]), "=f"(d[O+28]), "=f"(d[O+29]), "=f"(d[O+30]), "=f"(d[O+31]), "=f"(d[O+32]), "=f"(d[O+33]), "=f"(d[O+34]), "=f"(d[O+35]), "=f"(d[O+36]), "=f"(d[O+37]), "=f"(d[O+38]), "=f"(d[O+39]), "=f"(d[O+40]), "=f"(d[O+41]), "=f"(d[O+42]), "=f"(d[O+43]), "=f"(d[O+44]), "=f"(d[O+45]), "=f"(d[O+46]), "=f"(d[O+47]), "=f"(d[O+48]), "=f"(d[O+49]), "=f"(d[O+50]), "=f"(d[O+51]), "=f"(d[O+52]), "=f"(d[O+53]), "=f"(d[O+54]), "=f"(d[O+55]), "=f"(d[O+56]), "=f"(d[O+57]), "=f"(d[O+58]), "=f"(d[O+59]), "=f"(d[O+60]), "=f"(d[O+61]), "=f"(d[O+62]), "=f"(d[O+63])
   : "l"(da), "l"(db), "n"(TB & 1), "n"(TB >> 1));
  else asm volatile("{\n.reg .pred p;\nsetp.ne.b32 p, %68, 0;\nwgmma.mma_async.sync.aligned.m64n128k16.f32.bf16.bf16 {%0,%1,%2,%3,%4,%5,%6,%7,%8,%9,%10,%11,%12,%13,%14,%15,%16,%17,%18,%19,%20,%21,%22,%23,%24,%25,%26,%27,%28,%29,%30,%31,%32,%33,%34,%35,%36,%37,%38,%39,%40,%41,%42,%43,%44,%45,%46,%47,%48,%49,%50,%51,%52,%53,%54,%55,%56,%57,%58,%59,%60,%61,%62,%63}, %64, %65, p, 1, 1, %67, %66;\n}"
   : "+f"(d[O+0]), "+f"(d[O+1]), "+f"(d[O+2]), "+f"(d[O+3]), "+f"(d[O+4]), "+f"(d[O+5]), "+f"(d[O+6]), "+f"(d[O+7]), "+f"(d[O+8]), "+f"(d[O+9]), "+f"(d[O+10]), "+f"(d[O+11]), "+f"(d[O+12]), "+f"(d[O+13]), "+f"(d[O+14]), "+f"(d[O+15]), "+f"(d[O+16]), "+f"(d[O+17]), "+f"(d[O+18]), "+f"(d[O+19]), "+f"(d[O+20]), "+f"(d[O+21]), "+f"(d[O+22]), "+f"(d[O+23]), "+f"(d[O+24]), "+f"(d[O+25]), "+f"(d[O+26]), "+f"(d[O+27]), "+f"(d[O+28]), "+f"(d[O+29]), "+f"(d[O+30]), "+f"(d[O+31]), "+f"(d[O+32]), "+f"(d[O+33]), "+f"(d[O+34]), "+f"(d[O+35]), "+f"(d[O+36]), "+f"(d[O+37]), "+f"(d[O+38]), "+f"(d[O+39]), "+f"(d[O+40]), "+f"(d[O+41]), "+f"(d[O+42]), "+f"(d[O+43]), "+f"(d[O+44]), "+f"(d[O+45]), "+f"(d[O+46]), "+f"(d[O+47]), "+f"(d[O+48]), "+f"(d[O+49]), "+f"(d[O+50]), "+f"(d[O+51]), "+f"(d[O+52]), "+f"(d[O+53]), "+f"(d[O+54]), "+f"(d[O+55]), "+f"(d[O+56]), "+f"(d[O+57]), "+f"(d[O+58]), "+f"(d[O+59]), "+f"(d[O+60]), "+f"(d[O+61]), "+f"(d[O+62]), "+f"(d[O+63])
   : "l"(da), "l"(db), "n"(TB & 1), "n"(TB >> 1), "r"(sd));
}
template<int O,int TB,int ACC,int NN> __device__ __forceinline__ void mma_rs128(float (&d)[NN], uint32_t a0, uint32_t a1, uint32_t a2, uint32_t a3, uint64_t db, int sd = 0){
  if constexpr (ACC == 1) asm volatile("wgmma.mma_async.sync.aligned.m64n128k16.f32.bf16.bf16 {%0,%1,%2,%3,%4,%5,%6,%7,%8,%9,%10,%11,%12,%13,%14,%15,%16,%17,%18,%19,%20,%21,%22,%23,%24,%25,%26,%27,%28,%29,%30,%31,%32,%33,%34,%35,%36,%37,%38,%39,%40,%41,%42,%43,%44,%45,%46,%47,%48,%49,%50,%51,%52,%53,%54,%55,%56,%57,%58,%59,%60,%61,%62,%63}, {%64,%65,%66,%67}, %68, 1, 1, 1, %69;"
   : "+f"(d[O+0]), "+f"(d[O+1]), "+f"(d[O+2]), "+f"(d[O+3]), "+f"(d[O+4]), "+f"(d[O+5]), "+f"(d[O+6]), "+f"(d[O+7]), "+f"(d[O+8]), "+f"(d[O+9]), "+f"(d[O+10]), "+f"(d[O+11]), "+f"(d[O+12]), "+f"(d[O+13]), "+f"(d[O+14]), "+f"(d[O+15]), "+f"(d[O+16]), "+f"(d[O+17]), "+f"(d[O+18]), "+f"(d[O+19]), "+f"(d[O+20]), "+f"(d[O+21]), "+f"(d[O+22]), "+f"(d[O+23]), "+f"(d[O+24]), "+f"(d[O+25]), "+f"(d[O+26]), "+f"(d[O+27]), "+f"(d[O+28]), "+f"(d[O+29]), "+f"(d[O+30]), "+f"(d[O+31]), "+f"(d[O+32]), "+f"(d[O+33]), "+f"(d[O+34]), "+f"(d[O+35]), "+f"(d[O+36]), "+f"(d[O+37]), "+f"(d[O+38]), "+f"(d[O+39]), "+f"(d[O+40]), "+f"(d[O+41]), "+f"(d[O+42]), "+f"(d[O+43]), "+f"(d[O+44]), "+f"(d[O+45]), "+f"(d[O+46]), "+f"(d[O+47]), "+f"(d[O+48]), "+f"(d[O+49]), "+f"(d[O+50]), "+f"(d[O+51]), "+f"(d[O+52]), "+f"(d[O+53]), "+f"(d[O+54]), "+f"(d[O+55]), "+f"(d[O+56]), "+f"(d[O+57]), "+f"(d[O+58]), "+f"(d[O+59]), "+f"(d[O+60]), "+f"(d[O+61]), "+f"(d[O+62]), "+f"(d[O+63])
   : "r"(a0), "r"(a1), "r"(a2), "r"(a3), "l"(db), "n"(TB));
  else if constexpr (ACC == 0) asm volatile("wgmma.mma_async.sync.aligned.m64n128k16.f32.bf16.bf16 {%0,%1,%2,%3,%4,%5,%6,%7,%8,%9,%10,%11,%12,%13,%14,%15,%16,%17,%18,%19,%20,%21,%22,%23,%24,%25,%26,%27,%28,%29,%30,%31,%32,%33,%34,%35,%36,%37,%38,%39,%40,%41,%42,%43,%44,%45,%46,%47,%48,%49,%50,%51,%52,%53,%54,%55,%56,%57,%58,%59,%60,%61,%62,%63}, {%64,%65,%66,%67}, %68, 0, 1, 1, %69;"
   : "=f"(d[O+0]), "=f"(d[O+1]), "=f"(d[O+2]), "=f"(d[O+3]), "=f"(d[O+4]), "=f"(d[O+5]), "=f"(d[O+6]), "=f"(d[O+7]), "=f"(d[O+8]), "=f"(d[O+9]), "=f"(d[O+10]), "=f"(d[O+11]), "=f"(d[O+12]), "=f"(d[O+13]), "=f"(d[O+14]), "=f"(d[O+15]), "=f"(d[O+16]), "=f"(d[O+17]), "=f"(d[O+18]), "=f"(d[O+19]), "=f"(d[O+20]), "=f"(d[O+21]), "=f"(d[O+22]), "=f"(d[O+23]), "=f"(d[O+24]), "=f"(d[O+25]), "=f"(d[O+26]), "=f"(d[O+27]), "=f"(d[O+28]), "=f"(d[O+29]), "=f"(d[O+30]), "=f"(d[O+31]), "=f"(d[O+32]), "=f"(d[O+33]), "=f"(d[O+34]), "=f"(d[O+35]), "=f"(d[O+36]), "=f"(d[O+37]), "=f"(d[O+38]), "=f"(d[O+39]), "=f"(d[O+40]), "=f"(d[O+41]), "=f"(d[O+42]), "=f"(d[O+43]), "=f"(d[O+44]), "=f"(d[O+45]), "=f"(d[O+46]), "=f"(d[O+47]), "=f"(d[O+48]), "=f"(d[O+49]), "=f"(d[O+50]), "=f"(d[O+51]), "=f"(d[O+52]), "=f"(d[O+53]), "=f"(d[O+54]), "=f"(d[O+55]), "=f"(d[O+56]), "=f"(d[O+57]), "=f"(d[O+58]), "=f"(d[O+59]), "=f"(d[O+60]), "=f"(d[O+61]), "=f"(d[O+62]), "=f"(d[O+63])
   : "r"(a0), "r"(a1), "r"(a2), "r"(a3), "l"(db), "n"(TB));
  else asm volatile("{\n.reg .pred p;\nsetp.ne.b32 p, %70, 0;\nwgmma.mma_async.sync.aligned.m64n128k16.f32.bf16.bf16 {%0,%1,%2,%3,%4,%5,%6,%7,%8,%9,%10,%11,%12,%13,%14,%15,%16,%17,%18,%19,%20,%21,%22,%23,%24,%25,%26,%27,%28,%29,%30,%31,%32,%33,%34,%35,%36,%37,%38,%39,%40,%41,%42,%43,%44,%45,%46,%47,%48,%49,%50,%51,%52,%53,%54,%55,%56,%57,%58,%59,%60,%61,%62,%63}, {%64,%65,%66,%67}, %68, p, 1, 1, %69;\n}"
   : "+f"(d[O+0]), "+f"(d[O+1]), "+f"(d[O+2]), "+f"(d[O+3]), "+f"(d[O+4]), "+f"(d[O+5]), "+f"(d[O+6]), "+f"(d[O+7]), "+f"(d[O+8]), "+f"(d[O+9]), "+f"(d[O+10]), "+f"(d[O+11]), "+f"(d[O+12]), "+f"(d[O+13]), "+f"(d[O+14]), "+f"(d[O+15]), "+f"(d[O+16]), "+f"(d[O+17]), "+f"(d[O+18]), "+f"(d[O+19]), "+f"(d[O+20]), "+f"(d[O+21]), "+f"(d[O+22]), "+f"(d[O+23]), "+f"(d[O+24]), "+f"(d[O+25]), "+f"(d[O+26]), "+f"(d[O+27]), "+f"(d[O+28]), "+f"(d[O+29]), "+f"(d[O+30]), "+f"(d[O+31]), "+f"(d[O+32]), "+f"(d[O+33]), "+f"(d[O+34]), "+f"(d[O+35]), "+f"(d[O+36]), "+f"(d[O+37]), "+f"(d[O+38]), "+f"(d[O+39]), "+f"(d[O+40]), "+f"(d[O+41]), "+f"(d[O+42]), "+f"(d[O+43]), "+f"(d[O+44]), "+f"(d[O+45]), "+f"(d[O+46]), "+f"(d[O+47]), "+f"(d[O+48]), "+f"(d[O+49]), "+f"(d[O+50]), "+f"(d[O+51]), "+f"(d[O+52]), "+f"(d[O+53]), "+f"(d[O+54]), "+f"(d[O+55]), "+f"(d[O+56]), "+f"(d[O+57]), "+f"(d[O+58]), "+f"(d[O+59]), "+f"(d[O+60]), "+f"(d[O+61]), "+f"(d[O+62]), "+f"(d[O+63])
   : "r"(a0), "r"(a1), "r"(a2), "r"(a3), "l"(db), "n"(TB), "r"(sd));
}

#define NEARLY 0
#define XAHEAD 3
#define HEADN 6
#define WBATCH 1
#define WB 4
#define WSLEEP 20
#define XSPREAD 2
#define NOSEND 0
#define MSPLIT 3
#define PFALL 1
#define L2PF 1
#define STAG 0
#define SPACE 100
#define WPF 1
#define WAFTER 7
#define WPACE 0
#define GATE_AT 4
#define TPACE 40
#define PFMODE 0
#define MAPMODE 1
template <int V> struct IC { static constexpr int value = V; };
struct Maps { CUtensorMap x, ft, g64, u64, e, wr, wi, xs, ts, t, g32, u32, d224, o; };

constexpr int NCTA = 130;
constexpr int U = 16384;
constexpr int TB = 36864;
constexpr int OFF_RING = 8 * U, OFF_Z = 9 * U, OFF_XB = 12 * U, OFF_T = 13 * U, OFF_D = OFF_T;
constexpr int OFF_BAR = 14 * U, OFF_SP = OFF_BAR + 512, OFF_G = OFF_SP + 1024 + 128;
constexpr int SMEM_BYTES = OFF_G + 512;
constexpr int B_FX = 0, B_FA = 8, B_FT = 12, B_Z = 16, B_W = 24, B_HX = 25, B_TL = 26, B_HP = 27, B_WR = 30, B_E0 = 34;
constexpr int B_EA = 35, B_ET = 39, B_PZ = 43, B_RDY = 45, B_FE = 46;
constexpr int B_T = 50, B_XS = 51, B_G = 53, NBAR = 54;
__host__ __device__ constexpr int rslot(int n) { return n & 3; }
__host__ __device__ constexpr int rpar(int n) { return (n >> 2) & 1; }

__global__ void __cluster_dims__(2, 1, 1) __launch_bounds__(512, 1)
fused_kernel(Work* __restrict__ ws, const uint16_t* __restrict__ dtab, const __nv_bfloat16* __restrict__ w_r, const __nv_bfloat16* __restrict__ w_i,
             const __nv_bfloat16* __restrict__ gate_w, const __grid_constant__ Maps maps) {
  extern __shared__ __align__(1024) uint8_t smem[];
  const uint32_t sb = smem_u32(smem);
  const uint32_t bars = sb + OFF_BAR;
  const int tid = threadIdx.x, lane = tid & 31;
  const int warp = __shfl_sync(0xffffffffu, tid >> 5, 0);
  const bool helper = blockIdx.x >= 128;
  const int cl = (blockIdx.x >> 1) & 63, rank = blockIdx.x & 1;
  const int q4 = (cl & 1) | ((cl >> 2) & 2), rb = ((cl >> 1) & 3) | ((cl >> 4) << 2);
  const int j = 2 * q4 + rank;
  const int f_full = 448 * q4 + (rank ? 256 : 0);
  const int f_half = 448 * q4 + (rank ? 224 : 192);
  const int kg = 2 * j + (rb >> 3), tn = rb & 7;

  if (tid == 64) { PROF_EV(0); PROF_CK(40); }
  if (warp < 8) {
    asm volatile("barrier.cluster.arrive.relaxed.aligned;" ::: "memory");
    asm volatile("setmaxnreg.inc.sync.aligned.u32 192;");
    if (!helper) {
      const int wg = warp >> 2, w = warp & 3, g = lane >> 2;
      const bool elect = (tid & 127) == 0;
      float cX[32], cA[64], cB[64], cC[64], ci[64], ct[64];
      const int zero = blockIdx.x >> 16;
      uint32_t h[56], yf[16];
      const uint32_t d0 = (sb & 0x3FFFF) >> 4;
      const uint32_t dK = d0 | (1u << 16), dN = d0 | (512u << 16);
      const uint32_t dX = dK + wg * 512;
      constexpr uint32_t RING = OFF_RING >> 4;
      auto waitA = [&](int n) { mbar_wait(bars + 8 * (B_FA + rslot(n)), rpar(n)); };
      auto freeA = [&](int n) { mbar_arrive_if(elect, bars + 8 * (B_EA + rslot(n))); };
      auto nop = [] {};

      asm volatile("bar.sync 0, 384;" ::: "memory");
#pragma unroll 1
      for (int i = 0; i < 4; i++) {
        const uint64_t dx = d128(dX + i * 2048), df = d128(dK + (OFF_XB >> 4) + (i & 1) * 1024);
        mbar_wait(bars + 8 * (B_FX + 2 * i), 0);
        wg_fence();
        mma_ss64<0, 0, 2>(cX, df, dx, i);
        mma_ss64<0, 0, 1>(cX, df + 2, dx + 2);
        wg_commit(); wg_wait<1>();
        mbar_arrive_if(elect && i, bars + 8 * (B_EA + rslot(i - 1)));
        mma_ss64<0, 0, 1>(cX, df + 4, dx + 4);
        mma_ss64<0, 0, 1>(cX, df + 6, dx + 6);
        if (i == 0 && tid == 0) PROF_EV(1);
        mbar_wait(bars + 8 * (B_FX + 2 * i + 1), 0);
        wg_fence();
#pragma unroll
        for (int k = 0; k < 4; k++) mma_ss64<0, 0, 1>(cX, df + (512 + k * 2), dx + (1024 + k * 2));
        wg_commit();
        waitA(i);
        wg_fence();
        const uint64_t da = d128(dX + i * 1024), db = d128(dN + RING + i * 1024);
        mma_ss128<0, 1, 2>(cA, da, db, i);
        wg_commit(); wg_wait<1>();
        mbar_arrive_if(elect, bars + 8 * (B_FE + i));
#pragma unroll
        for (int k = 1; k < 4; k++) mma_ss128<0, 1, 1>(cA, da + k * 2, db + k * 128);
        wg_commit();
      }
      fence_regs<0, 32>(cX);
#pragma unroll
      for (int e = 0; e < 16; e++) yf[e] = pack_pin(cX[2 * e], cX[2 * e + 1]);
      if (tid == 0) { PROF_EV(2); PROF_CK(42); }
      {
        waitA(4); mbar_wait(bars + 8 * B_E0, 0);
        const uint64_t de = d128(dN + (wg ? RING : OFF_XB >> 4));
        wg_fence();
        mma_rs128<0, 1, 0>(cB, yf[0], yf[1], yf[2], yf[3], de);
        wg_commit();
        wg_wait<1>();
        freeA(3);
#pragma unroll
        for (int k = 1; k < 4; k++) mma_rs128<0, 1, 1>(cB, yf[4 * k], yf[4 * k + 1], yf[4 * k + 2], yf[4 * k + 3], de + k * 128);
        wg_commit();
      }
      bool rel = false;
      auto acquire = [&](int n) {
        rel = elect;
        if (!mbar_try(bars + 8 * (B_FA + rslot(n)), rpar(n))) { wg_wait<0>(); freeA(n - 1); rel = false; waitA(n); }
      };
      auto freeP = [&](int n) { mbar_arrive_if(rel, bars + 8 * (B_EA + rslot(n - 1))); };
      auto ffn_step = [&](auto first, auto split, float (&acc)[64], int n, int kb, auto done, auto work) {
        constexpr int SPLIT = decltype(split)::value;
        acquire(n);
        wg_fence();
        const uint64_t dx = d128(dX + kb * 1024), db = d128(dN + RING + rslot(n) * 1024);
        mma_ss128<0, 1, decltype(first)::value>(acc, dx, db, kb);
#pragma unroll
        for (int k = 1; k < SPLIT; k++) mma_ss128<0, 1, 1>(acc, dx + k * 2, db + k * 128);
        wg_commit();
        work();
        wg_wait<1>();
        freeP(n);
        done();
        if (SPLIT < 4) {
          wg_fence();
#pragma unroll
          for (int k = SPLIT; k < 4; k++) mma_ss128<0, 1, 1>(acc, dx + k * 2, db + k * 128);
          wg_commit();
        }
      };
      {
        const int s0 = 2 * rb + wg, kr = 2 * ((s0 & 1) | ((s0 & 4) >> 1));
        const int m = lane >> 3, r = lane & 7;
        const uint32_t a0 = sb + OFF_XB + wg * 8192 + (((w >> 1) * 8 + (m >> 1)) * 2 + (w & 1)) * 256 + (m & 1) * 128 + ((r ^ (kr + (m & 1))) << 4);
        ffn_step(IC<1>(), IC<4>(), cA, 5, 4, [&] { fence_regs<0, 64>(cB); }, nop);
        asm volatile("bar.sync 5, 256;" ::: "memory");
        auto stage = [&](int i) {
          stsm4t(a0 + i * 1024, pack_bf16(cB[8 * i] - cB[34 + 8 * i], cB[8 * i + 1] - cB[35 + 8 * i]),
                 pack_bf16(cB[32 + 8 * i] + cB[8 * i + 2], cB[33 + 8 * i] + cB[8 * i + 3]),
                 pack_bf16(cB[8 * i + 4] - cB[38 + 8 * i], cB[8 * i + 5] - cB[39 + 8 * i]),
                 pack_bf16(cB[36 + 8 * i] + cB[8 * i + 6], cB[37 + 8 * i] + cB[8 * i + 7]));
          if (j == 0 && w == 0) {
            const uint32_t a1 = r ? sb + OFF_SP + 1024 : sb + OFF_SP + wg * 512 + (m & 1) * 256 + (m >> 1) * 128;
#pragma unroll
            for (int n = 2 * i; n < 2 * i + 2; n++)
              asm volatile("stmatrix.sync.aligned.m8n8.x4.shared.b16 [%0], {%1,%2,%3,%4};" ::"r"(a1 + ((n ^ (kr + (m >> 1)) ^ r) << 4)),
                           "r"(pack_bf16(cB[4 * n], cB[4 * n + 1])), "r"(pack_bf16(cB[4 * n + 2], cB[4 * n + 3])),
                           "r"(pack_bf16(cB[32 + 4 * n], cB[33 + 4 * n])), "r"(pack_bf16(cB[34 + 4 * n], cB[35 + 4 * n])) : "memory");
          }
        };
        auto publish = [&] {
          asm volatile("fence.proxy.async.shared::cta;" ::: "memory");
          __syncwarp();
          mbar_arrive_if(lane == 0, bars + 8 * (B_XS + wg));
          if (tid == 0) PROF_EV(3);
        };
        stage(0); stage(1);
        ffn_step(IC<1>(), IC<1>(), cA, 6, 5, nop, nop);
        stage(2); stage(3);
        ffn_step(IC<1>(), IC<1>(), cA, 7, 6, nop, nop);
        publish();
        ffn_step(IC<1>(), IC<1>(), cA, 8, 7, nop, nop);
      }
      float g0 = 0.f, g1 = 0.f;
      uint32_t tag = 0;
      auto glu = [&](auto& acc, int half, int ho, int i0, int i1) {
#pragma unroll
        for (int i = i0; i < i1; i++) {
          const float o = 1.0f - ((i & 1) ? g1 : g0);
          asm volatile("" : "+f"(acc[2 * i]), "+f"(acc[2 * i + 1]), "+f"(acc[half + 2 * i]), "+f"(acc[half + 1 + 2 * i])::"memory");
          h[ho + i] = pack_pin(fmaxf(acc[2 * i], 0.f) * acc[half + 2 * i] * o, fmaxf(acc[2 * i + 1], 0.f) * acc[half + 1 + 2 * i] * o);
        }
      };
      ffn_step(IC<2>(), IC<1>(), cB, 9, zero, nop, nop);
#pragma unroll 1
      for (int kb = 1; kb < 8; kb++)
        ffn_step(IC<1>(), IC<1>(), cB, 9 + kb, kb, nop, [&] {
          if (kb == 4 + wg) {
            mbar_wait(bars + 8 * B_G, 0);
            const uint32_t gb0 = *(const uint32_t*)(smem + OFF_G + (wg * 64 + w * 16 + g) * 4), gb1 = *(const uint32_t*)(smem + OFF_G + (wg * 64 + w * 16 + g + 8) * 4);
            tag = gb0 & 1; g0 = __uint_as_float(gb0 & ~1u); g1 = __uint_as_float(gb1 & ~1u);
            glu(cA, 32, 0, 0, 8);
          } else if (kb == 6 + wg) glu(cA, 32, 0, 8, 16);
        });
      if (tid == 0) { PROF_EV(4); PROF_CK(43); }
      ffn_step(IC<0>(), IC<1>(), cC, 17, 0, nop, nop);
#pragma unroll 1
      for (int kb = 1; kb < 8; kb++)
        ffn_step(IC<1>(), IC<1>(), cC, 17 + kb, kb, nop, [&] {
          if (kb == 1 + wg) glu(cB, 32, 16, 0, 8);
          else if (kb == 3 + wg) glu(cB, 32, 16, 8, 16);
        });
      if (tid == 0) { PROF_EV(5); PROF_CK(44); }
      auto m_step = [&](auto first, int i) {
        acquire(25 + i);
        wg_fence();
        const uint64_t dx = d128(dX + i * 2048), dm = d64(dN + RING + rslot(25 + i) * 1024);
        mma_ss64<0, 1, decltype(first)::value>(ct, dx, dm);
#pragma unroll
        for (int k = 1; k < MSPLIT; k++) mma_ss64<0, 1, 1>(ct, dx + ((k >> 2) * 1024 + (k & 3) * 2), dm + k * 64);
        wg_commit();
        wg_wait<1>();
        mbar_arrive_if(rel && i < 3, bars + 8 * (B_EA + rslot(24 + i)));
        mbar_arrive_if(elect && i, bars + 8 * (B_ET + i - 1));
        wg_fence();
#pragma unroll
        for (int k = MSPLIT; k < 8; k++) mma_ss64<0, 1, 1>(ct, dx + ((k >> 2) * 1024 + (k & 3) * 2), dm + k * 64);
        wg_commit();
      };
      auto freeT = [&](int t) { mbar_arrive_if(elect, bars + 8 * (B_ET + t)); };
      m_step(IC<0>(), 0);
#pragma unroll 1
      for (int i = 1; i < 5; i++) {
        if (i == 1 + wg) glu(cC, 32, 32, 0, 8);
        else if (i == 3 + wg) glu(cC, 32, 32, 8, 16);
        if (i < 4) m_step(IC<1>(), i);
      }
      waitA(29 + wg);
      if (tid == 0) PROF_EV(6);
      if (tid == 128) PROF_EV(27);
      mbar_wait(bars + 8 * (j == 0 ? B_T : B_TL), 0);
      if (tid == 0) { PROF_EV(7); PROF_CK(45); }
      wg_fence();
      {
        const uint64_t dt = d128(dN + (OFF_T >> 4) + wg * 512), de = d128(dK + RING + (1 + wg) * 1024);
        mma_ss64<0, 1, 0>(ci, de, dt);
        mma_ss64<32, 1, 0>(ci, de + 512, dt);
#pragma unroll
        for (int k = 1; k < 4; k++) {
          mma_ss64<0, 1, 1>(ci, de + k * 2, dt + k * 128);
          mma_ss64<32, 1, 1>(ci, de + (512 + k * 2), dt + k * 128);
        }
        wg_commit();
        wg_wait<1>();
        freeT(3);
        fence_regs<0, 32>(ct);
        glu(ct, 16, 48, 0, 8);
      }

      auto twait = [&](uint32_t bar, uint32_t par, int) { mbar_wait(bar, par); };
      const int fo = warp * 128 + lane;
      auto fetch = [&](uint4 (&pv)[4], int z) {
        twait(bars + 8 * (z < 4 ? B_Z + 2 * z + wg : B_HP + z - 4), 0, 8 + z);
        const uint8_t* src = smem + (z < 5 ? OFF_Z + z * U : (z - 5) * U) + fo * 16;
#pragma unroll
        for (int i = 0; i < 4; i++) pv[i] = *(const uint4*)(src + i * 512);
      };
      auto check = [&](uint4 (&pv)[4], int z) {
        const uint32_t t0 = (uint32_t)clock();
        while (__any_sync(0xffffffffu, ((pv[0].x ^ tag) | (pv[1].x ^ tag) | (pv[2].x ^ tag) | (pv[3].x ^ tag)) & 1)) {
#pragma unroll
          for (int i = 0; i < 4; i++) pv[i] = ld_x4(ws->part + (size_t)((rb * 8 + j) * 3 + z - 4) * 1024 + fo + i * 32);
          spin_guard(t0);
        }
#pragma unroll
        for (int i = 0; i < 4; i++) pv[i].x &= ~1u;
      };
      auto head = [&](auto off, int t, bool init) {
        constexpr int O = decltype(off)::value;
        twait(bars + 8 * (B_FT + (t & 3)), t >> 2, t);
        const uint64_t db = d128(dN + (t & 3) * (TB >> 4) + rank * 256);
        wg_fence();
        mma_rs64<O, 1, 2>(ct, h[0], h[1], h[2], h[3], db, zero + init);
#pragma unroll
        for (int k = 1; k < 6; k++) mma_rs64<O, 1, 1>(ct, h[4 * k], h[4 * k + 1], h[4 * k + 2], h[4 * k + 3], db + k * 128);
        wg_commit();
        wg_wait<1>();
      };
      auto rest = [&](auto off, int t, int z) {
        constexpr int O = decltype(off)::value, P = 32 - O;
        const uint64_t db = d128(dN + (t & 3) * (TB >> 4)), dw = db + rank * 256, dm = db + (rank ? 0 : 1536);
        wg_fence();
#pragma unroll
        for (int k = 6; k < 12; k++) mma_rs64<O, 1, 1>(ct, h[4 * k], h[4 * k + 1], h[4 * k + 2], h[4 * k + 3], dw + k * 128);
        wg_commit();
        uint4 pv[4];
        if (z >= 0) fetch(pv, z);
        wg_fence();
#pragma unroll
        for (int k = 0; k < 2; k++) mma_rs64<O, 1, 1>(ct, h[48 + 4 * k], h[49 + 4 * k], h[50 + 4 * k], h[51 + 4 * k], dm + k * 128);
#pragma unroll
        for (int k = 0; k < 4; k++) mma_rs64<O, 1, 1>(ct, yf[4 * k], yf[4 * k + 1], yf[4 * k + 2], yf[4 * k + 3], db + (14 + k) * 128);
        wg_commit();
        if (z >= 0) {
          if (z >= 4) check(pv, z);
#pragma unroll
          for (int i = 0; i < 4; i++) {
            const uint32_t a[4] = {pv[i].x, pv[i].y, pv[i].z, pv[i].w};
#pragma unroll
            for (int e = 0; e < 4; e++) { ct[P + 8 * i + 2 * e] = bf_lo(a[e]); ct[P + 8 * i + 2 * e + 1] = bf_hi(a[e]); }
          }
        }
      };
      const uint32_t peerZ = mapa(sb + OFF_Z + fo * 16, rank ^ 1), peerB = mapa(bars + 8 * (B_Z + wg), rank ^ 1);
      auto send = [&](auto off, int t) {
        constexpr int O = decltype(off)::value;
        fence_regs<O, 32>(ct);
        const bool grid = t >= 3 && t < 6;
        const int z = grid ? t - 3 : t == 6 ? 3 : t;
        uint32_t pk[16];
#pragma unroll
        for (int i = 0; i < 16; i++) pk[i] = pack_bf16(ct[O + 2 * i], ct[O + 2 * i + 1]);
        if (grid) {
          const int owner = rb * 8 + 2 * ((q4 + z + 1) & 3) + rank;
          uint4* dst = ws->part + (size_t)(owner * 3 + z) * 1024 + fo;
#pragma unroll
          for (int i = 0; i < 4; i++) st_x4(dst + i * 32, (pk[4 * i] & ~1u) | tag, pk[4 * i + 1], pk[4 * i + 2], pk[4 * i + 3]);
          __syncwarp();
          hint_add_if(lane == 0, &ws->cntP[32 * owner + z]);
        } else {
#pragma unroll
          for (int i = 0; i < 4; i++)
            asm volatile("st.async.weak.shared::cluster.mbarrier::complete_tx::bytes.v4.b32 [%0], {%1,%2,%3,%4}, [%5];" ::"r"(peerZ + z * U + i * 512),
                         "r"(pk[4 * i]), "r"(pk[4 * i + 1]), "r"(pk[4 * i + 2]), "r"(pk[4 * i + 3]), "r"(peerB + 16 * z) : "memory");
        }
      };
      asm volatile("barrier.cluster.wait.aligned;" ::: "memory");
      head(IC<0>(), 0, false);
      if (elect) asm volatile("mbarrier.arrive.shared::cluster.b64 _, [%0];" ::"r"(mapa(bars + 8 * B_RDY, rank ^ 1)) : "memory");
      mbar_arrive_if(elect, bars + 8 * (B_PZ + 1));
      fence_regs<0, 64>(ci);
#pragma unroll
      for (int i = 0; i < 16; i++) {
        const float gg = ((i & 1) ? g1 : g0) * (2.0f / (2048.0f * 512.0f));
        if (i & 2) yf[i] = pack_pin((ci[2 * i] - ci[28 + 2 * i]) * gg, (ci[2 * i + 1] - ci[29 + 2 * i]) * gg);
        else yf[i] = pack_pin((ci[2 * i] + ci[36 + 2 * i]) * gg, (ci[2 * i + 1] + ci[37 + 2 * i]) * gg);
      }
      if (tid == 0) PROF_EV(8);
      if (tid == 128) PROF_EV(28);
#pragma unroll 1
      for (int t = 0;; t += 2) {
        rest(IC<0>(), t, t - 2);
        head(IC<32>(), t + 1, t >= 2);
        mbar_arrive_if(elect && t < 6, bars + 8 * (B_ET + t));
        if (t == 0) twait(bars + 8 * B_RDY, 0, 15);
        send(IC<0>(), t);
        rest(IC<32>(), t + 1, (t & 2) ? t - 1 : -1);
        if (t == 6) break;
        head(IC<0>(), t + 2, t == 2);
        mbar_arrive_if(elect && t < 4, bars + 8 * (B_ET + t + 1));
        send(IC<32>(), t + 1);
      }
      if (tid == 0) { PROF_EV(9); PROF_CK(46); }
      if (tid == 128) PROF_EV(29);
      {
        float (&sum)[64] = ct;
        uint4 p2[4], p3[4];
        fetch(p3, 3);
        if (tid == 0) PROF_EV(25);
        fetch(p2, 6);
        if (tid == 0) PROF_EV(24);
        check(p2, 6);
#pragma unroll
        for (int i = 0; i < 4; i++) {
          const uint32_t b[4] = {p2[i].x, p2[i].y, p2[i].z, p2[i].w}, c[4] = {p3[i].x, p3[i].y, p3[i].z, p3[i].w};
#pragma unroll
          for (int e = 0; e < 4; e++) {
            sum[8 * i + 2 * e] += bf_lo(c[e]) + bf_lo(b[e]);
            sum[8 * i + 2 * e + 1] += bf_hi(c[e]) + bf_hi(b[e]);
          }
        }
        if (tid == 0) PROF_EV(14);
        wg_wait<0>();
        fence_regs<32, 32>(ct);
#pragma unroll
        for (int i = 0; i < 32; i++) sum[i] += ct[32 + i];
        const uint32_t stg = sb + OFF_T + warp * 2048;
        const int mr = (lane & 7) + ((lane >> 3) & 1) * 8, mc = lane >> 4;
#pragma unroll
        for (int i = 0; i < 4; i++) {
          const uint32_t a = stg + mr * 128 + (((2 * i + mc) ^ (mr & 7)) << 4);
          asm volatile("stmatrix.sync.aligned.m8n8.x4.shared.b16 [%0], {%1,%2,%3,%4};" ::"r"(a), "r"(pack_bf16(sum[8 * i], sum[8 * i + 1])),
                       "r"(pack_bf16(sum[8 * i + 2], sum[8 * i + 3])), "r"(pack_bf16(sum[8 * i + 4], sum[8 * i + 5])),
                       "r"(pack_bf16(sum[8 * i + 6], sum[8 * i + 7])) : "memory");
        }
        asm volatile("fence.proxy.async.shared::cta;" ::: "memory");
        __syncwarp();
        if (elect_one()) {
          asm volatile("cp.async.bulk.tensor.3d.global.shared::cta.bulk_group [%0, {%2, %3, %4}], [%1];" ::"l"(&maps.o), "r"(stg), "r"(64 * j),
                       "r"(16 * w), "r"(2 * rb + wg) : "memory");
          asm volatile("cp.async.bulk.commit_group;\ncp.async.bulk.wait_group.read 0;" ::: "memory");
        }
      }
      if (tid == 0) { PROF_EV(15); PROF_CK(41); }
      if (tid == 128) PROF_EV(30);
    }
  } else if (warp < 12) {
    asm volatile("setmaxnreg.dec.sync.aligned.u32 104;");
    asm volatile("barrier.cluster.arrive.relaxed.aligned;" ::: "memory");
    const int t = tid - 256, w = warp - 8;
    const uint32_t ep = ld_x1(&ws->epoch[blockIdx.x * 8]);
    const uint32_t tag = (ep + 1) & 1;
    auto w_issue = [&](const CUtensorMap* m) {
          if (elect_one()) { mbar_expect_tx(bars + 8 * (B_WR + w), 3072); tma4d(sb + OFF_T + w * 3072, m, bars + 8 * (B_WR + w), 16 * kg, 0, 2 * w, tn); }
          __syncwarp();
    };
    auto gate_rows = [&] {
      const int r = 16 * j + 4 * w + (lane >> 3);
      const uint4* pg = (const uint4*)gate_w + (lane & 7);
      {
        float a = 0.f;
        asm volatile("bar.sync 4, 256;" ::: "memory");
#pragma unroll 1
        for (int hf = 0; hf < 2; hf++) {
          uint4 v[4], u[4];
#pragma unroll
          for (int kb = 0; kb < 4; kb++) v[kb] = __ldg(pg + (4 * hf + kb) * 8);
          mbar_wait(bars + 8 * (B_FE + 1 + 2 * hf), 0);
          if (hf) w_issue(&maps.wr);
#pragma unroll
          for (int kb = 0; kb < 4; kb++) u[kb] = *(const uint4*)(smem + (4 * hf + kb) * U + r * 128 + (((lane ^ r) & 7) << 4));
#pragma unroll
          for (int kb = 0; kb < 4; kb++) {
            a = fmaf(bf_lo(u[kb].x), bf_lo(v[kb].x), a); a = fmaf(bf_hi(u[kb].x), bf_hi(v[kb].x), a);
            a = fmaf(bf_lo(u[kb].y), bf_lo(v[kb].y), a); a = fmaf(bf_hi(u[kb].y), bf_hi(v[kb].y), a);
            a = fmaf(bf_lo(u[kb].z), bf_lo(v[kb].z), a); a = fmaf(bf_hi(u[kb].z), bf_hi(v[kb].z), a);
            a = fmaf(bf_lo(u[kb].w), bf_lo(v[kb].w), a); a = fmaf(bf_hi(u[kb].w), bf_hi(v[kb].w), a);
          }
        }
#pragma unroll
        for (int o = 4; o; o >>= 1) a += __shfl_xor_sync(0xffffffffu, a, o);
        if ((lane & 7) == 0)
          asm volatile("st.relaxed.gpu.global.f32 [%0], %1;" ::"l"(ws->gate + rb * 128 + r), "f"(tagf(__fdividef(1.0f, 1.0f + __expf(-a)), tag)) : "memory");
        if (t == 0) PROF_EV(18);
      }
    };
    {
      const int g = lane >> 2, q = lane & 3;
      uint32_t wf[32];
      if (!helper) {
        gate_rows();
        const uint32_t wa = sb + OFF_T + w * (3072 + 4) + q * 48 + g * 2;
#pragma unroll 1
        for (int ri = 0; ri < 2; ri++) {
          mbar_wait(bars + 8 * (B_WR + w), ri);
#pragma unroll
          for (int n2 = 0; n2 < 32 / WB; n2++) {
            uint32_t v[WB];
#pragma unroll
            for (int i = 0; i < WB; i++) {
              const int e = n2 * WB + i;
              asm volatile("ld.shared.u16 %0, [%1];" : "=r"(v[i]) : "r"(wa + ((e >> 1) & 7) * 192 + (e & 1) * (1536 + 2) + (e >> 4) * 16) : "memory");
            }
#pragma unroll
            for (int i = 0; i < WB; i++) wf[n2 * WB + i] = __byte_perm(wf[n2 * WB + i], v[i], 0x5432);
            if (WSLEEP) { asm volatile("nanosleep.u32 %0;" ::"r"(WSLEEP + (v[WB - 1] >> 16)) : "memory"); }
          }
          __syncwarp();
          if (ri == 0) w_issue(&maps.wi);
        }
        asm volatile("bar.sync 1, 128;" ::: "memory");
        if (t == 0) PROF_EV(11);
      } else {
        asm volatile("bar.sync 4, 256;" ::: "memory");
        hint_wait(&ws->cntW[0], (ep + 1) * 128u);
        const uint32_t t0 = (uint32_t)clock();
#pragma unroll 1
        for (;;) {
          uint32_t bad = 0;
#pragma unroll
          for (int i = 0; i < 32; i++) {
            const float2 v = ld_x2((const float2*)ws->Wh + (i >> 4) * 2048 + 16 * w + g + 8 * (i & 1) + 64 * q + ((i >> 1) & 7) * 256);
            wf[i] = __float_as_uint(v.x); bad |= __float_as_uint(v.y) ^ tag;
          }
          if (!__any_sync(0xffffffffu, bad & 1)) break;
          spin_guard(t0);
        }
        if (t == 0) PROF_EV(11);
      }
      if (w == 0 && elect_one()) { mbar_expect_tx(bars + 8 * B_W, 8192); bulk_load(sb + OFF_D, dtab, 8192, bars + 8 * B_W); }
      if (!helper) {
        const uint32_t t0 = (uint32_t)clock();
        uint32_t v;
        do { v = ld_x1(ws->gate + rb * 128 + t); spin_guard(t0); } while (__any_sync(0xffffffffu, (v ^ tag) & 1));
        *(uint32_t*)(smem + OFF_G + t * 4) = v;
        __syncwarp();
        mbar_arrive_if(lane == 0, bars + 8 * B_G);
      }
      mbar_wait(bars + 8 * B_W, 0);
      mbar_wait(bars + 8 * B_HX, 0);
      if (t == 0) PROF_EV(12);
      const uint32_t dd = (sb & 0x3FFFF) >> 4;
      const uint64_t dF = d128((dd + (OFF_D >> 4)) | (512u << 16)), dI = d128((dd + (OFF_D >> 4)) | (1u << 16)), dA = d128((dd + (OFF_XB >> 4)) | (512u << 16));
      float az[32];
      const int zero = blockIdx.x >> 16;
      uint32_t pf[32];
#pragma unroll
      for (int mt = 0; mt < 2; mt++) {
        wg_fence();
        if (mt == 0) mma_ss64<0, 3, 0>(az, dA, dF);
        else mma_ss64<0, 3, 2>(az, dA + 512, dF, zero);
#pragma unroll
        for (int k = 1; k < 4; k++) mma_ss64<0, 3, 1>(az, dA + (mt * 512 + k * 128), dF + k * 128);
        wg_commit();
        wg_wait<0>();
        fence_regs<0, 32>(az);
#pragma unroll
        for (int i = 0; i < 16; i++) {
          const float wr = bf_lo(wf[16 * mt + i]), wi = bf_hi(wf[16 * mt + i]);
          pf[16 * mt + i] = pack_pin(fmaf(az[2 * i], wr, -az[2 * i + 1] * wi), fmaf(az[2 * i], wi, az[2 * i + 1] * wr));
        }
      }
      if (t == 0) PROF_EV(16);
#pragma unroll
      for (int mt = 0; mt < 2; mt++) {
        wg_fence();
        mma_rs64<0, 0, 2>(az, pf[16 * mt], pf[16 * mt + 1], pf[16 * mt + 2], pf[16 * mt + 3], dI, mt ? (int)helper : zero);
#pragma unroll
        for (int k = 1; k < 4; k++) mma_rs64<0, 0, 1>(az, pf[16 * mt + 4 * k], pf[16 * mt + 4 * k + 1], pf[16 * mt + 4 * k + 2], pf[16 * mt + 4 * k + 3], dI + k * 2);
        wg_commit();
        wg_wait<0>();
        fence_regs<0, 32>(az);
        if (!helper) {
          const int m = lane >> 3, r = lane & 7;
          const int sl = 2 * (m >> 1) + ((r >> 1) & 1) + 4 * (r >> 2);
          const uint32_t a0 = sb + OFF_XB + (2 * w + (m & 1)) * 2048 + sl * 64 + (((mt * 2 + (r & 1)) ^ (sl >> 1)) << 4);
#pragma unroll
          for (int i = 0; i < 4; i++)
            stsm4t(a0 + i * 512, pack_bf16(az[8 * i], az[8 * i + 1]), pack_bf16(az[8 * i + 2], az[8 * i + 3]), pack_bf16(az[8 * i + 4], az[8 * i + 5]),
                   pack_bf16(az[8 * i + 6], az[8 * i + 7]));
        }
      }
      if (helper) {
#pragma unroll
        for (int i = 0; i < 16; i++) {
          const int n = i >> 1, s0 = 8 * (n >> 1) + 2 * (n & 1) + (q & 1) + 4 * (q >> 1);
          if ((n & 1) == (int)(blockIdx.x & 1)) st_u2(ws->Ts + s0 * 64 + 16 * w + g + 8 * (i & 1), pack_bf16(az[2 * i], az[2 * i + 1]), tag);
        }
        __syncwarp();
        hint_add_if(lane == 0, &ws->cntH[0]);
        if (t == 0) { ws->epoch[blockIdx.x * 8] = ep + 1; PROF_EV(13); }
      } else {
        asm volatile("fence.proxy.async.shared::cta;" ::: "memory");
        __syncwarp();
        if (elect_one()) {
          if (t == 0) PROF_EV(17);
          if (SPACE) __nanosleep(SPACE * w);
          asm volatile("cp.async.bulk.tensor.3d.global.shared::cta.bulk_group [%0, {%2, %3, %4}], [%1];" ::"l"(&maps.ts), "r"(sb + OFF_XB + w * 4096),
                       "r"(32 * kg), "r"(0), "r"(8 * tn + 2 * w) : "memory");
          bulk_done_signal(&ws->cntT[32 * j]);
          if (t == 96) PROF_EV(13);
        }
        __syncwarp();
        if (j == 0) {
          hint_wait(&ws->cntH[0], (ep + 1) * 8u);
          const uint32_t t0 = (uint32_t)clock();
          float2 v;
          do { v = ld_x2((const float2*)ws->Ts + 2 * rb * 64 + t); spin_guard(t0); } while (__any_sync(0xffffffffu, (__float_as_uint(v.y) ^ tag) & 1));
          mbar_wait(bars + 8 * B_TL, 0);
          const uint32_t u = __float_as_uint(v.x);
          *(uint16_t*)(smem + OFF_T + t * 128 + ((t & 7) << 4)) = (uint16_t)u;
          *(uint16_t*)(smem + OFF_T + t * 128 + (((t & 7) ^ 1) << 4)) = (uint16_t)(u >> 16);
          asm volatile("fence.proxy.async.shared::cta;" ::: "memory");
          __syncwarp();
          mbar_arrive_if(lane == 0, bars + 8 * B_T);
        }
      }
    }
  } else {
    asm volatile("setmaxnreg.dec.sync.aligned.u32 24;");
    auto xf_load = [&](int q) {
      const uint32_t fb = bars + 8 * (B_FX + q);
      mbar_expect_tx(fb, U + 8192);
      tma3d(sb + q * U, &maps.x, fb, 64 * q, 0, 2 * rb);
      if (q >= 4) mbar_wait(bars + 8 * (B_FE + ((q - 4) >> 1)), 0);
      tma2d(sb + OFF_XB + (q & 3) * 8192, &maps.ft, fb, 64 * q, 64 * j);
    };
    if (elect_one()) {
      if (warp == 14) {
#pragma unroll
        for (int i = 0; i < B_FT; i++) mbar_init(bars + 8 * i, 1);
        asm volatile("fence.mbarrier_init.release.cluster;" ::: "memory");
        if (!helper) {
#pragma unroll 1
          for (int n = 0; n < 2; n++) {
            const uint32_t fb = bars + 8 * (B_FA + n);
            xf_load(2 * n); xf_load(2 * n + 1);
            mbar_expect_tx(fb, U);
            tma2d(sb + OFF_RING + n * U, &maps.g64, fb, f_full, 64 * n);
            tma2d(sb + OFF_RING + n * U + 8192, &maps.u64, fb, f_full, 64 * n);
          }
        }
      } else if (warp == 15) {
#pragma unroll
        for (int i = B_FT; i < NBAR; i++) mbar_init(bars + 8 * i, i < B_EA ? 1 : i < B_T ? 2 : 4);
#pragma unroll
        for (int i = 0; i < 8; i++) mbar_expect_tx(bars + 8 * (B_Z + i), U / 2);
        asm volatile("fence.mbarrier_init.release.cluster;" ::: "memory");
        asm volatile("fence.proxy.async.shared::cta;" ::: "memory");
      } else if (warp == 13) {
#pragma unroll
        for (int i = 1; i < 4; i++) asm volatile("prefetch.tensormap [%0];" ::"l"((const char*)&maps + i * 128) : "memory");
      }
    }
    __syncwarp();
    asm volatile("bar.arrive 0, 384;" ::: "memory");
    asm volatile("bar.arrive 4, 256;" ::: "memory");
    __syncwarp();
    asm volatile("barrier.cluster.arrive.relaxed.aligned;" ::: "memory");
    asm volatile("bar.sync 3, 128;" ::: "memory");
    if (warp == 15 && !helper) {
        mbar_wait(bars + 8 * B_FE, 0);
        const uint32_t tag = (ld_x1(&ws->epoch[blockIdx.x * 8]) + 1) & 1;
        const int c = lane >> 4, jj = 16 * blockIdx.x + (lane & 15), jm = (2048 - jj) & 2047;
        const unsigned short* pr = (const unsigned short*)w_r + 256 * c;
        const unsigned short* pi = (const unsigned short*)w_i + 256 * c;
        const float wr = 0.25f * (bf_lo(__ldg(pr + jj * 257)) + bf_lo(__ldg(pr + jm * 257)));
        const float wi = 0.25f * (bf_lo(__ldg(pi + jj * 257)) - bf_lo(__ldg(pi + jm * 257)));
        st_u2(ws->Wh + c * 2048 + jj, c ? pack_bf16(-wi, wr) : pack_bf16(wr, wi), tag);
        __syncwarp();
        hint_add_if(lane == 0, &ws->cntW[0]);
      }
    if ((!helper || warp == 15) && elect_one()) {
      if (warp < 14) {
        const int p = warp - 12;
#pragma unroll 1
        for (int i = 4 + p; i < 14; i += 2) asm volatile("prefetch.tensormap [%0];" ::"l"((const char*)&maps + i * 128) : "memory");
#pragma unroll 1
        for (int n = 2; n < 31; n++) {
          const bool table = n == 4 || n >= 29;
          const int q = n < 4 ? n : n - 1;
          const CUtensorMap* m = table ? &maps.e : n >= 25 ? &maps.g32 + p : &maps.g64 + p;
          const int c0 = table ? 0 : n >= 25 ? f_half : f_full + 64 * (q >> 3);
          const int c1 = table ? (2 * rb + ((n & 1) ^ 1)) * 128 + 64 * p : n >= 25 ? 128 * (n - 25) : 64 * (q & 7);
          const uint32_t fb = bars + 8 * (B_FA + (n & 3)), dst = sb + OFF_RING + (n & 3) * U + p * 8192;
          if (n < 4) mbar_wait(bars + 8 * (B_FE + n - 2), 0);
          else mbar_wait(bars + 8 * (B_EA + (n & 3)), ((n >> 2) & 1) ^ 1);
          tma2d(dst, m, fb, c0, c1);
          if (p == 0) mbar_expect_tx(fb, U);
        }
      } else if (warp == 15) {
        const unsigned ep1 = ld_x1(&ws->epoch[blockIdx.x * 8]) + 1;
        flag_wait(&ws->cntX[helper ? 0 : 32 * j], ep1 * 16u);
        PROF_EV(22);
        mbar_expect_tx(bars + 8 * B_HX, U);
        bulk_load(sb + OFF_XB, ws->X + (size_t)(helper ? 128 : kg * 8 + tn) * 8192, U, bars + 8 * B_HX);
        if (!helper) {
          flag_wait(&ws->cntT[32 * j], ep1 * 64u);
          PROF_EV(23);
          mbar_expect_tx(bars + 8 * B_TL, U);
          tma3d(sb + OFF_T, &maps.t, bars + 8 * B_TL, 64 * j, 0, 2 * rb);
#pragma unroll 1
          for (int i = 0; i < 3; i++) {
            flag_wait(&ws->cntP[32 * (rb * 8 + j) + i], ep1 * 8u);
            mbar_wait(bars + 8 * (B_PZ + (i == 0)), 0);
            if (i == 2) PROF_EV(26);
            mbar_expect_tx(bars + 8 * (B_HP + i), U);
            bulk_load(sb + (i ? (i - 1) * U : OFF_T), ws->part + (size_t)((rb * 8 + j) * 3 + i) * 1024, U, bars + 8 * (B_HP + i));
          }
          ws->epoch[blockIdx.x * 8] = ep1;
        }
      } else {
#pragma unroll 1
        for (int q = 4; q < 8; q++) xf_load(q);
        mbar_wait(bars + 8 * (B_FE + 2), 0);
        mbar_expect_tx(bars + 8 * B_E0, U);
        tma2d(sb + OFF_XB, &maps.e, bars + 8 * B_E0, 0, 2 * rb * 128);
        tma2d(sb + OFF_XB + 8192, &maps.e, bars + 8 * B_E0, 0, 2 * rb * 128 + 64);
#pragma unroll 1
        for (int h2 = 0; h2 < 2; h2++) {
          const int s0 = 2 * rb + h2, sg = (s0 & ~6) | ((s0 & 2) << 1) | ((s0 & 4) >> 1);
          mbar_wait(bars + 8 * (B_XS + h2), 0);
#pragma unroll 1
          for (int c = 0; c < 2; c++) {
            asm volatile("cp.async.bulk.tensor.4d.global.shared::cta.bulk_group [%0, {%2, %3, %4, %5}], [%1];" ::"l"(&maps.xs),
                         "r"(sb + OFF_XB + h2 * 8192 + c * 4096), "r"(0), "r"(sg), "r"(0), "r"(16 * j + 8 * c) : "memory");
            if (j == 0)
              asm volatile("cp.async.bulk.global.shared::cta.bulk_group [%0], [%1], 256;" ::"l"(ws->X + 128 * 8192 + c * 4096 + sg * 128),
                           "r"(sb + OFF_SP + h2 * 512 + c * 256) : "memory");
            if (SPACE && h2 + c < 2) __nanosleep(SPACE);
          }
        }
        bulk_done_signal(&ws->cntX[32 * j]);
        PROF_EV(20);
        if (rb < 8) asm volatile("cp.async.bulk.prefetch.tensor.2d.L2.global [%0, {%1, %2}];" ::"l"(&maps.g32 + (rb >> 2)), "r"(f_half), "r"(128 * (rb & 3)) : "memory");
        else asm volatile("cp.async.bulk.prefetch.tensor.2d.L2.global [%0, {%1, %2}];" ::"l"(&maps.d224), "r"(64 * (rb - 8)), "r"(224 * j) : "memory");
#pragma unroll 1
        for (int t = 0; t < 8; t++) {
          const int i = t < 3 ? t + 1 : t < 6 ? t - 2 : 0;
          const int col = 64 * (2 * ((q4 + i) & 3) + ((t < 3 || t == 6) ? 1 - rank : rank));
          const uint32_t fb = bars + 8 * (B_FT + (t & 3)), dst = sb + (t & 3) * TB;
          mbar_wait(bars + 8 * (B_ET + (t == 2 ? 3 : t & 3)), t >> 2);
          mbar_expect_tx(fb, TB);
          tma2d(dst, &maps.d224, fb, col, 224 * j);
          if (t < 2) mbar_wait(bars + 8 * (B_ET + t + 1), 0);
          tma2d(dst + 28672, &maps.ft, fb, col, 64 * j);
        }
      }
    }
  }
}

typedef CUresult (*EncodeFn)(CUtensorMap*, CUtensorMapDataType, cuuint32_t, void*, const cuuint64_t*, const cuuint64_t*, const cuuint32_t*,
                             const cuuint32_t*, CUtensorMapInterleave, CUtensorMapSwizzle, CUtensorMapL2promotion, CUtensorMapFloatOOBfill);

static void encode(EncodeFn f, CUtensorMap* m, const void* base, int rank, const cuuint64_t* dims, const cuuint64_t* strides, const cuuint32_t* box,
                   CUtensorMapSwizzle sw) {
  cuuint32_t es[5] = {1, 1, 1, 1, 1};
  f(m, CU_TENSOR_MAP_DATA_TYPE_BFLOAT16, rank, (void*)base, dims, strides, box, es, CU_TENSOR_MAP_INTERLEAVE_NONE, sw,
    CU_TENSOR_MAP_L2_PROMOTION_L2_128B, CU_TENSOR_MAP_FLOAT_OOB_FILL_NONE);
}

extern "C" void kernel_launch(void* const* d_in, const int* in_sizes, int n_in, void* d_out, int out_size) {
  (void)in_sizes; (void)n_in; (void)out_size;
  const __nv_bfloat16* x = (const __nv_bfloat16*)d_in[0];
  const __nv_bfloat16* w_r = (const __nv_bfloat16*)d_in[1];
  const __nv_bfloat16* w_i = (const __nv_bfloat16*)d_in[2];
  const __nv_bfloat16* Wg = (const __nv_bfloat16*)d_in[4];
  const __nv_bfloat16* Wu = (const __nv_bfloat16*)d_in[5];
  const __nv_bfloat16* Wd = (const __nv_bfloat16*)d_in[6];
  const __nv_bfloat16* gw = (const __nv_bfloat16*)d_in[7];

  void* fp = nullptr; cudaDriverEntryPointQueryResult qr;
  cudaGetDriverEntryPoint("cuTensorMapEncodeTiled", &fp, cudaEnableDefault, &qr);
  EncodeFn enc = (EncodeFn)fp;
  void *pFT, *pET, *pDT, *pW;
  cudaGetSymbolAddress(&pDT, g_DT); cudaGetSymbolAddress(&pW, g_work);
  void *pX = ((Work*)pW)->X, *pT = ((Work*)pW)->T;
  cudaGetSymbolAddress(&pFT, g_FT); cudaGetSymbolAddress(&pET, g_ET);

  Maps mp;
  const CUtensorMapSwizzle S128 = CU_TENSOR_MAP_SWIZZLE_128B, S64 = CU_TENSOR_MAP_SWIZZLE_64B;
  { cuuint64_t d[3] = {512, 64, 32}, s[2] = {32768, 1024}; cuuint32_t b[3] = {64, 64, 2}, b2[3] = {64, 16, 1};
    encode(enc, &mp.x, x, 3, d, s, b, S128); encode(enc, &mp.o, d_out, 3, d, s, b2, S128); }
  { cuuint64_t d[2] = {512, 512}, s[1] = {1024}; cuuint32_t b[2] = {64, 64}; encode(enc, &mp.ft, pFT, 2, d, s, b, S128); }
  { cuuint64_t d[4] = {128, 32, 2, 129}, s[3] = {256, 8192, 16384}; cuuint32_t b[4] = {128, 1, 2, 8}; encode(enc, &mp.xs, pX, 4, d, s, b, CU_TENSOR_MAP_SWIZZLE_NONE); }
  { cuuint64_t d[3] = {512, 32, 64}, s[2] = {65536, 1024}; cuuint32_t b[3] = {32, 32, 2}; encode(enc, &mp.ts, pT, 3, d, s, b, S64); }
  { cuuint64_t d[3] = {512, 64, 32}, s[2] = {1024, 65536}; cuuint32_t b[3] = {64, 64, 2}; encode(enc, &mp.t, pT, 3, d, s, b, S128); }
  { cuuint64_t d[2] = {64, 4096}, s[1] = {128}; cuuint32_t b[2] = {64, 64}; encode(enc, &mp.e, pET, 2, d, s, b, S128); }
  { cuuint64_t d[2] = {1792, 512}, s[1] = {3584}; cuuint32_t b[2] = {64, 64}, b2[2] = {32, 128};
    encode(enc, &mp.g64, Wg, 2, d, s, b, S128); encode(enc, &mp.u64, Wu, 2, d, s, b, S128);
    encode(enc, &mp.g32, Wg, 2, d, s, b2, S64); encode(enc, &mp.u32, Wu, 2, d, s, b2, S64); }
  { cuuint64_t d[2] = {512, 1792}, s[1] = {1024}; cuuint32_t b[2] = {64, 224}; encode(enc, &mp.d224, Wd, 2, d, s, b, S128); }
  { cuuint64_t d[4] = {264, 32, 8, 8}, s[3] = {32896, 512, 4112}; cuuint32_t b[4] = {24, 32, 2, 1};
    encode(enc, &mp.wr, w_r, 4, d, s, b, CU_TENSOR_MAP_SWIZZLE_NONE); encode(enc, &mp.wi, w_i, 4, d, s, b, CU_TENSOR_MAP_SWIZZLE_NONE); }

  cudaFuncSetAttribute(fused_kernel, cudaFuncAttributeMaxDynamicSharedMemorySize, SMEM_BYTES);
  fused_kernel<<<NCTA, 512, SMEM_BYTES>>>((Work*)pW, (const uint16_t*)pDT, w_r, w_i, gw, mp);
}
```

```cpp
#include <cuda_runtime.h>
#include <cuda_bf16.h>
#include <cuda.h>
#include <stdint.h>

namespace tbl {
constexpr double PI = 3.14159265358979323846264338327950288;
constexpr double sin_s(double x) { double t = x, s = x; for (int n = 1; n < 12; n++) { t *= -x * x / ((2 * n) * (2 * n + 1)); s += t; } return s; }
constexpr double cos_s(double x) { double t = 1, s = 1; for (int n = 1; n < 12; n++) { t *= -x * x / ((2 * n - 1) * (2 * n)); s += t; } return s; }
constexpr double cos2048(int m) {
  m &= 2047; if (m > 1024) m = 2048 - m;
  bool neg = false; if (m > 512) { m = 1024 - m; neg = true; }
  double v = (m <= 256) ? cos_s(2 * PI * m / 2048) : sin_s(2 * PI * (512 - m) / 2048);
  return neg ? -v : v;
}
constexpr uint16_t to_bf16(double v) {
  if (v == 0) return 0;
  uint16_t s = 0; if (v < 0) { s = 0x8000; v = -v; }
  int e = 0; while (v >= 2) { v /= 2; e++; } while (v < 1) { v *= 2; e--; }
  double m = (v - 1) * 128; int mi = (int)m; double fr = m - mi;
  if (fr > 0.5 || (fr == 0.5 && (mi & 1))) mi++;
  if (mi == 128) { mi = 0; e++; }
  return (uint16_t)(s | ((e + 127) << 7) | mi);
}
struct CosT { uint16_t v[2048]; constexpr CosT() : v() { for (int i = 0; i < 2048; i++) v[i] = to_bf16(cos2048(i)); } };
struct alignas(1024) FT {
  uint16_t v[512 * 512];
  constexpr FT() : v() {
    CosT c;
    for (int r = 0; r < 512; r++) {
      int k = (r >> 4) * 8 + (r & 7), e = (r >> 3) & 1;
      int mul = 4 * k, add = e ? 512 : 0;
      if (k == 0 && e == 1) { mul = 1024; add = 0; }
      for (int d = 0; d < 512; d++) v[r * 512 + d] = c.v[(d * mul + add) & 2047];
    }
  }
};
struct alignas(1024) ET {
  uint16_t v[2048 * 128];
  constexpr ET() : v() {
    CosT c;
    for (int s = 0; s < 2048; s++)
      for (int j = 0; j < 64; j++) {
        const int o = (s & 31) * 8192 + (s >> 5) * 64 + j;
        v[o] = c.v[(s * j) & 2047]; v[o + 4096] = c.v[(s * j + 512) & 2047];
      }
  }
};
struct alignas(1024) DT {
  uint16_t v[64 * 64];
  constexpr DT() : v() {
    CosT c;
    for (int r = 0; r < 64; r++)
      for (int n = 0; n < 64; n++) {
        const int sg = r >> 1, s0 = (sg & ~6) | ((sg & 2) << 1) | ((sg & 4) >> 1), e = r & 1, f = n & 1;
        const int m = 64 * s0 * (n >> 1) + (e == f ? 0 : e ? -512 : 512);
        v[r * 64 + (((n >> 3) ^ (r & 7)) << 3) + (n & 7)] = c.v[m & 2047];
      }
  }
};
}

__device__ constexpr tbl::FT g_FT = tbl::FT();
__device__ constexpr tbl::ET g_ET = tbl::ET();
__device__ constexpr tbl::DT g_DT = tbl::DT();

struct alignas(1024) Work {
  unsigned epoch[132 * 8];
  unsigned cntX[8 * 32], cntT[8 * 32], cntP[128 * 32], cntW[32], cntH[32];
  alignas(16) float gate[16 * 128];
  alignas(16) uint2 Wh[2 * 2048];
  alignas(16) uint2 Ts[32 * 64];
  alignas(1024) uint16_t X[129 * 8192];
  alignas(1024) uint16_t T[32 * 64 * 512];
  alignas(1024) uint4 part[128 * 3 * 1024];
};
__device__ Work g_work;
#define PROF_EV(i) do {} while (0)
#define PROF_CK(i) do {} while (0)

__device__ __forceinline__ uint32_t smem_u32(const void* p) { return (uint32_t)__cvta_generic_to_shared(p); }
__device__ __forceinline__ void mbar_init(uint32_t bar, uint32_t cnt) { asm volatile("mbarrier.init.shared::cta.b64 [%0], %1;" ::"r"(bar), "r"(cnt)); }
__device__ __forceinline__ void mbar_expect_tx(uint32_t bar, uint32_t bytes) { asm volatile("mbarrier.arrive.expect_tx.shared::cta.b64 _, [%0], %1;" ::"r"(bar), "r"(bytes) : "memory"); }
__device__ __forceinline__ void mbar_arrive(uint32_t bar) { asm volatile("mbarrier.arrive.shared::cta.b64 _, [%0];" ::"r"(bar) : "memory"); }
__device__ __forceinline__ bool elect_one() {
  uint32_t p;
  asm volatile("{\n.reg .pred p;\nelect.sync _|p, 0xffffffff;\nselp.u32 %0, 1, 0, p;\n}" : "=r"(p));
  return p;
}
__device__ __forceinline__ void mbar_arrive_if(bool p, uint32_t bar) {
  asm volatile("{\n.reg .pred p;\nsetp.ne.b32 p, %1, 0;\n@p mbarrier.arrive.shared::cta.b64 _, [%0];\n}" ::"r"(bar), "r"((int)p) : "memory");
}
__device__ __forceinline__ void hint_add_if(bool p, unsigned* a) {
  asm volatile("{\n.reg .pred p;\nsetp.ne.b32 p, %1, 0;\n@p red.relaxed.gpu.global.add.u32 [%0], 1;\n}" ::"l"(a), "r"((int)p) : "memory");
}
__device__ __forceinline__ bool mbar_try(uint32_t bar, uint32_t parity) {
  uint32_t ok;
  asm volatile("{\n.reg .pred p;\nmbarrier.test_wait.parity.shared::cta.b64 p, [%1], %2;\nselp.u32 %0, 1, 0, p;\n}" : "=r"(ok) : "r"(bar), "r"(parity) : "memory");
  return ok;
}
__device__ __forceinline__ void mbar_wait(uint32_t bar, uint32_t parity) {
  asm volatile(
      "{\n.reg .pred p;\n.reg .u32 n;\nmov.u32 n, 0;\n"
      "W_LOOP:\nmbarrier.try_wait.parity.shared::cta.b64 p, [%0], %1;\n@p bra W_DONE;\n"
      "add.u32 n, n, 1;\nsetp.lt.u32 p, n, 0x40000;\n@p bra W_LOOP;\ntrap;\nW_DONE:\n}" ::"r"(bar), "r"(parity) : "memory");
}
__device__ __forceinline__ void bulk_load(uint32_t dst, const void* src, uint32_t bytes, uint32_t bar) {
  asm volatile("cp.async.bulk.shared::cluster.global.mbarrier::complete_tx::bytes [%0], [%1], %2, [%3];" ::"r"(dst), "l"(src), "r"(bytes), "r"(bar) : "memory");
}
__device__ __forceinline__ void cp16(uint32_t dst, const void* src) { asm volatile("cp.async.cg.shared.global [%0], [%1], 16;" ::"r"(dst), "l"(src) : "memory"); }
__device__ __forceinline__ void spin_guard(uint32_t t0) { if ((uint32_t)clock() - t0 > (1u << 30)) __trap(); }
__device__ __forceinline__ float tagf(float v, uint32_t tag) { return __uint_as_float((__float_as_uint(v) & ~1u) | tag); }
__device__ __forceinline__ float untag(float v) { return __uint_as_float(__float_as_uint(v) & ~1u); }
__device__ __forceinline__ void st_x2(float2* p, float a, float b) { asm volatile("st.relaxed.gpu.global.v2.f32 [%0], {%1,%2};" ::"l"(p), "f"(a), "f"(b) : "memory"); }
__device__ __forceinline__ float2 ld_x2(const float2* p) { float2 v; asm volatile("ld.relaxed.gpu.global.v2.f32 {%0,%1}, [%2];" : "=f"(v.x), "=f"(v.y) : "l"(p) : "memory"); return v; }
__device__ __forceinline__ void st_u2(uint2* p, uint32_t a, uint32_t b) { asm volatile("st.relaxed.gpu.global.v2.u32 [%0], {%1,%2};" ::"l"(p), "r"(a), "r"(b) : "memory"); }
__device__ __forceinline__ void prefetch2d(const CUtensorMap* m, int c0, int c1) { asm volatile("cp.async.bulk.prefetch.tensor.2d.L2.global [%0, {%1, %2}];" ::"l"(m), "r"(c0), "r"(c1) : "memory"); }
__device__ __forceinline__ void prefetch1d(const void* p, uint32_t bytes) { asm volatile("cp.async.bulk.prefetch.L2.global [%0], %1;" ::"l"(p), "r"(bytes) : "memory"); }
__device__ __forceinline__ uint32_t ld_x1(const void* p) { uint32_t v; asm volatile("ld.relaxed.gpu.global.u32 %0, [%1];" : "=r"(v) : "l"(p) : "memory"); return v; }
__device__ __forceinline__ uint4 ld_x4(const void* p) { uint4 v; asm volatile("ld.relaxed.gpu.global.v4.u32 {%0,%1,%2,%3}, [%4];" : "=r"(v.x), "=r"(v.y), "=r"(v.z), "=r"(v.w) : "l"(p) : "memory"); return v; }
__device__ __forceinline__ void st_x4(void* p, uint32_t a, uint32_t b, uint32_t c, uint32_t d) { asm volatile("st.relaxed.gpu.global.v4.u32 [%0], {%1,%2,%3,%4};" ::"l"(p), "r"(a), "r"(b), "r"(c), "r"(d) : "memory"); }
__device__ __forceinline__ uint32_t mapa(uint32_t a, uint32_t cta) { uint32_t r; asm volatile("mapa.shared::cluster.u32 %0, %1, %2;" : "=r"(r) : "r"(a), "r"(cta)); return r; }
__device__ __forceinline__ void stsm4t(uint32_t a, uint32_t r0, uint32_t r1, uint32_t r2, uint32_t r3) {
  asm volatile("stmatrix.sync.aligned.m8n8.x4.trans.shared.b16 [%0], {%1,%2,%3,%4};" ::"r"(a), "r"(r0), "r"(r1), "r"(r2), "r"(r3) : "memory");
}
__device__ __forceinline__ void hint_add(unsigned* p) { asm volatile("red.relaxed.gpu.global.add.u32 [%0], 1;" ::"l"(p) : "memory"); }
__device__ __forceinline__ void hint_wait(const unsigned* p, unsigned target) {
  const uint32_t t0 = (uint32_t)clock();
  while ((int)(ld_x1(p) - target) < 0) spin_guard(t0);
}
__device__ __forceinline__ void bulk_done_signal(unsigned* p) {
  asm volatile("cp.async.bulk.commit_group;\ncp.async.bulk.wait_group 0;\nfence.proxy.async.global;" ::: "memory");
  hint_add(p);
}
__device__ __forceinline__ void flag_wait(const unsigned* p, unsigned target) {
  hint_wait(p, target);
  asm volatile("fence.proxy.async.global;" ::: "memory");
}
__device__ __forceinline__ void tma2d(uint32_t dst, const CUtensorMap* m, uint32_t bar, int c0, int c1) {
  asm volatile("cp.async.bulk.tensor.2d.shared::cluster.global.mbarrier::complete_tx::bytes [%0], [%1, {%3, %4}], [%2];" ::"r"(dst), "l"(m), "r"(bar), "r"(c0), "r"(c1) : "memory");
}
__device__ __forceinline__ void tma3d(uint32_t dst, const CUtensorMap* m, uint32_t bar, int c0, int c1, int c2) {
  asm volatile("cp.async.bulk.tensor.3d.shared::cluster.global.mbarrier::complete_tx::bytes [%0], [%1, {%3, %4, %5}], [%2];" ::"r"(dst), "l"(m), "r"(bar), "r"(c0), "r"(c1), "r"(c2) : "memory");
}
__device__ __forceinline__ void tma4d(uint32_t dst, const CUtensorMap* m, uint32_t bar, int c0, int c1, int c2, int c3) {
  asm volatile("cp.async.bulk.tensor.4d.shared::cluster.global.mbarrier::complete_tx::bytes [%0], [%1, {%3, %4, %5, %6}], [%2];" ::"r"(dst), "l"(m), "r"(bar), "r"(c0), "r"(c1), "r"(c2), "r"(c3) : "memory");
}
__device__ __forceinline__ void wg_fence() { asm volatile("wgmma.fence.sync.aligned;" ::: "memory"); }
__device__ __forceinline__ void wg_commit() { asm volatile("wgmma.commit_group.sync.aligned;" ::: "memory"); }
template <int N> __device__ __forceinline__ void wg_wait() { asm volatile("wgmma.wait_group.sync.aligned %0;" ::"n"(N) : "memory"); }
template <int O, int N, int NN> __device__ __forceinline__ void fence_regs(float (&d)[NN]) {
#pragma unroll
  for (int i = 0; i < N; i++) asm volatile("" : "+f"(d[O + i])::"memory");
}
__device__ __forceinline__ uint32_t pack_bf16(float lo, float hi) {
  uint32_t r; asm("cvt.rn.bf16x2.f32 %0, %1, %2;" : "=r"(r) : "f"(hi), "f"(lo)); return r;
}
__device__ __forceinline__ uint32_t pack_pin(float lo, float hi) {
  uint32_t r; asm volatile("cvt.rn.bf16x2.f32 %0, %1, %2;" : "=r"(r) : "f"(hi), "f"(lo) : "memory"); return r;
}
__device__ __forceinline__ float bf_lo(uint32_t u) { return __uint_as_float(u << 16); }
__device__ __forceinline__ float bf_hi(uint32_t u) { return __uint_as_float(u & 0xffff0000u); }

__device__ __forceinline__ uint64_t d128(uint32_t lo) { uint64_t d; asm("mov.b64 %0, {%1, 0x40000040};" : "=l"(d) : "r"(lo)); return d; }
__device__ __forceinline__ uint64_t d64(uint32_t lo) { uint64_t d; asm("mov.b64 %0, {%1, 0x80000020};" : "=l"(d) : "r"(lo)); return d; }
template<int O,int TB,int ACC,int NN> __device__ __forceinline__ void mma_ss64(float (&d)[NN], uint64_t da, uint64_t db, int sd = 0){
  if constexpr (ACC == 1) asm volatile("wgmma.mma_async.sync.aligned.m64n64k16.f32.bf16.bf16 {%0,%1,%2,%3,%4,%5,%6,%7,%8,%9,%10,%11,%12,%13,%14,%15,%16,%17,%18,%19,%20,%21,%22,%23,%24,%25,%26,%27,%28,%29,%30,%31}, %32, %33, 1, 1, 1, %35, %34;"
   : "+f"(d[O+0]), "+f"(d[O+1]), "+f"(d[O+2]), "+f"(d[O+3]), "+f"(d[O+4]), "+f"(d[O+5]), "+f"(d[O+6]), "+f"(d[O+7]), "+f"(d[O+8]), "+f"(d[O+9]), "+f"(d[O+10]), "+f"(d[O+11]), "+f"(d[O+12]), "+f"(d[O+13]), "+f"(d[O+14]), "+f"(d[O+15]), "+f"(d[O+16]), "+f"(d[O+17]), "+f"(d[O+18]), "+f"(d[O+19]), "+f"(d[O+20]), "+f"(d[O+21]), "+f"(d[O+22]), "+f"(d[O+23]), "+f"(d[O+24]), "+f"(d[O+25]), "+f"(d[O+26]), "+f"(d[O+27]), "+f"(d[O+28]), "+f"(d[O+29]), "+f"(d[O+30]), "+f"(d[O+31])
   : "l"(da), "l"(db), "n"(TB & 1), "n"(TB >> 1));
  else if constexpr (ACC == 0) asm volatile("wgmma.mma_async.sync.aligned.m64n64k16.f32.bf16.bf16 {%0,%1,%2,%3,%4,%5,%6,%7,%8,%9,%10,%11,%12,%13,%14,%15,%16,%17,%18,%19,%20,%21,%22,%23,%24,%25,%26,%27,%28,%29,%30,%31}, %32, %33, 0, 1, 1, %35, %34;"
   : "=f"(d[O+0]), "=f"(d[O+1]), "=f"(d[O+2]), "=f"(d[O+3]), "=f"(d[O+4]), "=f"(d[O+5]), "=f"(d[O+6]), "=f"(d[O+7]), "=f"(d[O+8]), "=f"(d[O+9]), "=f"(d[O+10]), "=f"(d[O+11]), "=f"(d[O+12]), "=f"(d[O+13]), "=f"(d[O+14]), "=f"(d[O+15]), "=f"(d[O+16]), "=f"(d[O+17]), "=f"(d[O+18]), "=f"(d[O+19]), "=f"(d[O+20]), "=f"(d[O+21]), "=f"(d[O+22]), "=f"(d[O+23]), "=f"(d[O+24]), "=f"(d[O+25]), "=f"(d[O+26]), "=f"(d[O+27]), "=f"(d[O+28]), "=f"(d[O+29]), "=f"(d[O+30]), "=f"(d[O+31])
   : "l"(da), "l"(db), "n"(TB & 1), "n"(TB >> 1));
  else asm volatile("{\n.reg .pred p;\nsetp.ne.b32 p, %36, 0;\nwgmma.mma_async.sync.aligned.m64n64k16.f32.bf16.bf16 {%0,%1,%2,%3,%4,%5,%6,%7,%8,%9,%10,%11,%12,%13,%14,%15,%16,%17,%18,%19,%20,%21,%22,%23,%24,%25,%26,%27,%28,%29,%30,%31}, %32, %33, p, 1, 1, %35, %34;\n}"
   : "+f"(d[O+0]), "+f"(d[O+1]), "+f"(d[O+2]), "+f"(d[O+3]), "+f"(d[O+4]), "+f"(d[O+5]), "+f"(d[O+6]), "+f"(d[O+7]), "+f"(d[O+8]), "+f"(d[O+9]), "+f"(d[O+10]), "+f"(d[O+11]), "+f"(d[O+12]), "+f"(d[O+13]), "+f"(d[O+14]), "+f"(d[O+15]), "+f"(d[O+16]), "+f"(d[O+17]), "+f"(d[O+18]), "+f"(d[O+19]), "+f"(d[O+20]), "+f"(d[O+21]), "+f"(d[O+22]), "+f"(d[O+23]), "+f"(d[O+24]), "+f"(d[O+25]), "+f"(d[O+26]), "+f"(d[O+27]), "+f"(d[O+28]), "+f"(d[O+29]), "+f"(d[O+30]), "+f"(d[O+31])
   : "l"(da), "l"(db), "n"(TB & 1), "n"(TB >> 1), "r"(sd));
}
template<int O,int TB,int ACC,int NN> __device__ __forceinline__ void mma_rs64(float (&d)[NN], uint32_t a0, uint32_t a1, uint32_t a2, uint32_t a3, uint64_t db, int sd = 0){
  if constexpr (ACC == 1) asm volatile("wgmma.mma_async.sync.aligned.m64n64k16.f32.bf16.bf16 {%0,%1,%2,%3,%4,%5,%6,%7,%8,%9,%10,%11,%12,%13,%14,%15,%16,%17,%18,%19,%20,%21,%22,%23,%24,%25,%26,%27,%28,%29,%30,%31}, {%32,%33,%34,%35}, %36, 1, 1, 1, %37;"
   : "+f"(d[O+0]), "+f"(d[O+1]), "+f"(d[O+2]), "+f"(d[O+3]), "+f"(d[O+4]), "+f"(d[O+5]), "+f"(d[O+6]), "+f"(d[O+7]), "+f"(d[O+8]), "+f"(d[O+9]), "+f"(d[O+10]), "+f"(d[O+11]), "+f"(d[O+12]), "+f"(d[O+13]), "+f"(d[O+14]), "+f"(d[O+15]), "+f"(d[O+16]), "+f"(d[O+17]), "+f"(d[O+18]), "+f"(d[O+19]), "+f"(d[O+20]), "+f"(d[O+21]), "+f"(d[O+22]), "+f"(d[O+23]), "+f"(d[O+24]), "+f"(d[O+25]), "+f"(d[O+26]), "+f"(d[O+27]), "+f"(d[O+28]), "+f"(d[O+29]), "+f"(d[O+30]), "+f"(d[O+31])
   : "r"(a0), "r"(a1), "r"(a2), "r"(a3), "l"(db), "n"(TB));
  else if constexpr (ACC == 0) asm volatile("wgmma.mma_async.sync.aligned.m64n64k16.f32.bf16.bf16 {%0,%1,%2,%3,%4,%5,%6,%7,%8,%9,%10,%11,%12,%13,%14,%15,%16,%17,%18,%19,%20,%21,%22,%23,%24,%25,%26,%27,%28,%29,%30,%31}, {%32,%33,%34,%35}, %36, 0, 1, 1, %37;"
   : "=f"(d[O+0]), "=f"(d[O+1]), "=f"(d[O+2]), "=f"(d[O+3]), "=f"(d[O+4]), "=f"(d[O+5]), "=f"(d[O+6]), "=f"(d[O+7]), "=f"(d[O+8]), "=f"(d[O+9]), "=f"(d[O+10]), "=f"(d[O+11]), "=f"(d[O+12]), "=f"(d[O+13]), "=f"(d[O+14]), "=f"(d[O+15]), "=f"(d[O+16]), "=f"(d[O+17]), "=f"(d[O+18]), "=f"(d[O+19]), "=f"(d[O+20]), "=f"(d[O+21]), "=f"(d[O+22]), "=f"(d[O+23]), "=f"(d[O+24]), "=f"(d[O+25]), "=f"(d[O+26]), "=f"(d[O+27]), "=f"(d[O+28]), "=f"(d[O+29]), "=f"(d[O+30]), "=f"(d[O+31])
   : "r"(a0), "r"(a1), "r"(a2), "r"(a3), "l"(db), "n"(TB));
  else asm volatile("{\n.reg .pred p;\nsetp.ne.b32 p, %38, 0;\nwgmma.mma_async.sync.aligned.m64n64k16.f32.bf16.bf16 {%0,%1,%2,%3,%4,%5,%6,%7,%8,%9,%10,%11,%12,%13,%14,%15,%16,%17,%18,%19,%20,%21,%22,%23,%24,%25,%26,%27,%28,%29,%30,%31}, {%32,%33,%34,%35}, %36, p, 1, 1, %37;\n}"
   : "+f"(d[O+0]), "+f"(d[O+1]), "+f"(d[O+2]), "+f"(d[O+3]), "+f"(d[O+4]), "+f"(d[O+5]), "+f"(d[O+6]), "+f"(d[O+7]), "+f"(d[O+8]), "+f"(d[O+9]), "+f"(d[O+10]), "+f"(d[O+11]), "+f"(d[O+12]), "+f"(d[O+13]), "+f"(d[O+14]), "+f"(d[O+15]), "+f"(d[O+16]), "+f"(d[O+17]), "+f"(d[O+18]), "+f"(d[O+19]), "+f"(d[O+20]), "+f"(d[O+21]), "+f"(d[O+22]), "+f"(d[O+23]), "+f"(d[O+24]), "+f"(d[O+25]), "+f"(d[O+26]), "+f"(d[O+27]), "+f"(d[O+28]), "+f"(d[O+29]), "+f"(d[O+30]), "+f"(d[O+31])
   : "r"(a0), "r"(a1), "r"(a2), "r"(a3), "l"(db), "n"(TB), "r"(sd));
}
template<int O,int TB,int ACC,int NN> __device__ __forceinline__ void mma_ss128(float (&d)[NN], uint64_t da, uint64_t db, int sd = 0){
  if constexpr (ACC == 1) asm volatile("wgmma.mma_async.sync.aligned.m64n128k16.f32.bf16.bf16 {%0,%1,%2,%3,%4,%5,%6,%7,%8,%9,%10,%11,%12,%13,%14,%15,%16,%17,%18,%19,%20,%21,%22,%23,%24,%25,%26,%27,%28,%29,%30,%31,%32,%33,%34,%35,%36,%37,%38,%39,%40,%41,%42,%43,%44,%45,%46,%47,%48,%49,%50,%51,%52,%53,%54,%55,%56,%57,%58,%59,%60,%61,%62,%63}, %64, %65, 1, 1, 1, %67, %66;"
   : "+f"(d[O+0]), "+f"(d[O+1]), "+f"(d[O+2]), "+f"(d[O+3]), "+f"(d[O+4]), "+f"(d[O+5]), "+f"(d[O+6]), "+f"(d[O+7]), "+f"(d[O+8]), "+f"(d[O+9]), "+f"(d[O+10]), "+f"(d[O+11]), "+f"(d[O+12]), "+f"(d[O+13]), "+f"(d[O+14]), "+f"(d[O+15]), "+f"(d[O+16]), "+f"(d[O+17]), "+f"(d[O+18]), "+f"(d[O+19]), "+f"(d[O+20]), "+f"(d[O+21]), "+f"(d[O+22]), "+f"(d[O+23]), "+f"(d[O+24]), "+f"(d[O+25]), "+f"(d[O+26]), "+f"(d[O+27]), "+f"(d[O+28]), "+f"(d[O+29]), "+f"(d[O+30]), "+f"(d[O+31]), "+f"(d[O+32]), "+f"(d[O+33]), "+f"(d[O+34]), "+f"(d[O+35]), "+f"(d[O+36]), "+f"(d[O+37]), "+f"(d[O+38]), "+f"(d[O+39]), "+f"(d[O+40]), "+f"(d[O+41]), "+f"(d[O+42]), "+f"(d[O+43]), "+f"(d[O+44]), "+f"(d[O+45]), "+f"(d[O+46]), "+f"(d[O+47]), "+f"(d[O+48]), "+f"(d[O+49]), "+f"(d[O+50]), "+f"(d[O+51]), "+f"(d[O+52]), "+f"(d[O+53]), "+f"(d[O+54]), "+f"(d[O+55]), "+f"(d[O+56]), "+f"(d[O+57]), "+f"(d[O+58]), "+f"(d[O+59]), "+f"(d[O+60]), "+f"(d[O+61]), "+f"(d[O+62]), "+f"(d[O+63])
   : "l"(da), "l"(db), "n"(TB & 1), "n"(TB >> 1));
  else if constexpr (ACC == 0) asm volatile("wgmma.mma_async.sync.aligned.m64n128k16.f32.bf16.bf16 {%0,%1,%2,%3,%4,%5,%6,%7,%8,%9,%10,%11,%12,%13,%14,%15,%16,%17,%18,%19,%20,%21,%22,%23,%24,%25,%26,%27,%28,%29,%30,%31,%32,%33,%34,%35,%36,%37,%38,%39,%40,%41,%42,%43,%44,%45,%46,%47,%48,%49,%50,%51,%52,%53,%54,%55,%56,%57,%58,%59,%60,%61,%62,%63}, %64, %65, 0, 1, 1, %67, %66;"
   : "=f"(d[O+0]), "=f"(d[O+1]), "=f"(d[O+2]), "=f"(d[O+3]), "=f"(d[O+4]), "=f"(d[O+5]), "=f"(d[O+6]), "=f"(d[O+7]), "=f"(d[O+8]), "=f"(d[O+9]), "=f"(d[O+10]), "=f"(d[O+11]), "=f"(d[O+12]), "=f"(d[O+13]), "=f"(d[O+14]), "=f"(d[O+15]), "=f"(d[O+16]), "=f"(d[O+17]), "=f"(d[O+18]), "=f"(d[O+19]), "=f"(d[O+20]), "=f"(d[O+21]), "=f"(d[O+22]), "=f"(d[O+23]), "=f"(d[O+24]), "=f"(d[O+25]), "=f"(d[O+26]), "=f"(d[O+27]), "=f"(d[O+28]), "=f"(d[O+29]), "=f"(d[O+30]), "=f"(d[O+31]), "=f"(d[O+32]), "=f"(d[O+33]), "=f"(d[O+34]), "=f"(d[O+35]), "=f"(d[O+36]), "=f"(d[O+37]), "=f"(d[O+38]), "=f"(d[O+39]), "=f"(d[O+40]), "=f"(d[O+41]), "=f"(d[O+42]), "=f"(d[O+43]), "=f"(d[O+44]), "=f"(d[O+45]), "=f"(d[O+46]), "=f"(d[O+47]), "=f"(d[O+48]), "=f"(d[O+49]), "=f"(d[O+50]), "=f"(d[O+51]), "=f"(d[O+52]), "=f"(d[O+53]), "=f"(d[O+54]), "=f"(d[O+55]), "=f"(d[O+56]), "=f"(d[O+57]), "=f"(d[O+58]), "=f"(d[O+59]), "=f"(d[O+60]), "=f"(d[O+61]), "=f"(d[O+62]), "=f"(d[O+63])
   : "l"(da), "l"(db), "n"(TB & 1), "n"(TB >> 1));
  else asm volatile("{\n.reg .pred p;\nsetp.ne.b32 p, %68, 0;\nwgmma.mma_async.sync.aligned.m64n128k16.f32.bf16.bf16 {%0,%1,%2,%3,%4,%5,%6,%7,%8,%9,%10,%11,%12,%13,%14,%15,%16,%17,%18,%19,%20,%21,%22,%23,%24,%25,%26,%27,%28,%29,%30,%31,%32,%33,%34,%35,%36,%37,%38,%39,%40,%41,%42,%43,%44,%45,%46,%47,%48,%49,%50,%51,%52,%53,%54,%55,%56,%57,%58,%59,%60,%61,%62,%63}, %64, %65, p, 1, 1, %67, %66;\n}"
   : "+f"(d[O+0]), "+f"(d[O+1]), "+f"(d[O+2]), "+f"(d[O+3]), "+f"(d[O+4]), "+f"(d[O+5]), "+f"(d[O+6]), "+f"(d[O+7]), "+f"(d[O+8]), "+f"(d[O+9]), "+f"(d[O+10]), "+f"(d[O+11]), "+f"(d[O+12]), "+f"(d[O+13]), "+f"(d[O+14]), "+f"(d[O+15]), "+f"(d[O+16]), "+f"(d[O+17]), "+f"(d[O+18]), "+f"(d[O+19]), "+f"(d[O+20]), "+f"(d[O+21]), "+f"(d[O+22]), "+f"(d[O+23]), "+f"(d[O+24]), "+f"(d[O+25]), "+f"(d[O+26]), "+f"(d[O+27]), "+f"(d[O+28]), "+f"(d[O+29]), "+f"(d[O+30]), "+f"(d[O+31]), "+f"(d[O+32]), "+f"(d[O+33]), "+f"(d[O+34]), "+f"(d[O+35]), "+f"(d[O+36]), "+f"(d[O+37]), "+f"(d[O+38]), "+f"(d[O+39]), "+f"(d[O+40]), "+f"(d[O+41]), "+f"(d[O+42]), "+f"(d[O+43]), "+f"(d[O+44]), "+f"(d[O+45]), "+f"(d[O+46]), "+f"(d[O+47]), "+f"(d[O+48]), "+f"(d[O+49]), "+f"(d[O+50]), "+f"(d[O+51]), "+f"(d[O+52]), "+f"(d[O+53]), "+f"(d[O+54]), "+f"(d[O+55]), "+f"(d[O+56]), "+f"(d[O+57]), "+f"(d[O+58]), "+f"(d[O+59]), "+f"(d[O+60]), "+f"(d[O+61]), "+f"(d[O+62]), "+f"(d[O+63])
   : "l"(da), "l"(db), "n"(TB & 1), "n"(TB >> 1), "r"(sd));
}
template<int O,int TB,int ACC,int NN> __device__ __forceinline__ void mma_rs128(float (&d)[NN], uint32_t a0, uint32_t a1, uint32_t a2, uint32_t a3, uint64_t db, int sd = 0){
  if constexpr (ACC == 1) asm volatile("wgmma.mma_async.sync.aligned.m64n128k16.f32.bf16.bf16 {%0,%1,%2,%3,%4,%5,%6,%7,%8,%9,%10,%11,%12,%13,%14,%15,%16,%17,%18,%19,%20,%21,%22,%23,%24,%25,%26,%27,%28,%29,%30,%31,%32,%33,%34,%35,%36,%37,%38,%39,%40,%41,%42,%43,%44,%45,%46,%47,%48,%49,%50,%51,%52,%53,%54,%55,%56,%57,%58,%59,%60,%61,%62,%63}, {%64,%65,%66,%67}, %68, 1, 1, 1, %69;"
   : "+f"(d[O+0]), "+f"(d[O+1]), "+f"(d[O+2]), "+f"(d[O+3]), "+f"(d[O+4]), "+f"(d[O+5]), "+f"(d[O+6]), "+f"(d[O+7]), "+f"(d[O+8]), "+f"(d[O+9]), "+f"(d[O+10]), "+f"(d[O+11]), "+f"(d[O+12]), "+f"(d[O+13]), "+f"(d[O+14]), "+f"(d[O+15]), "+f"(d[O+16]), "+f"(d[O+17]), "+f"(d[O+18]), "+f"(d[O+19]), "+f"(d[O+20]), "+f"(d[O+21]), "+f"(d[O+22]), "+f"(d[O+23]), "+f"(d[O+24]), "+f"(d[O+25]), "+f"(d[O+26]), "+f"(d[O+27]), "+f"(d[O+28]), "+f"(d[O+29]), "+f"(d[O+30]), "+f"(d[O+31]), "+f"(d[O+32]), "+f"(d[O+33]), "+f"(d[O+34]), "+f"(d[O+35]), "+f"(d[O+36]), "+f"(d[O+37]), "+f"(d[O+38]), "+f"(d[O+39]), "+f"(d[O+40]), "+f"(d[O+41]), "+f"(d[O+42]), "+f"(d[O+43]), "+f"(d[O+44]), "+f"(d[O+45]), "+f"(d[O+46]), "+f"(d[O+47]), "+f"(d[O+48]), "+f"(d[O+49]), "+f"(d[O+50]), "+f"(d[O+51]), "+f"(d[O+52]), "+f"(d[O+53]), "+f"(d[O+54]), "+f"(d[O+55]), "+f"(d[O+56]), "+f"(d[O+57]), "+f"(d[O+58]), "+f"(d[O+59]), "+f"(d[O+60]), "+f"(d[O+61]), "+f"(d[O+62]), "+f"(d[O+63])
   : "r"(a0), "r"(a1), "r"(a2), "r"(a3), "l"(db), "n"(TB));
  else if constexpr (ACC == 0) asm volatile("wgmma.mma_async.sync.aligned.m64n128k16.f32.bf16.bf16 {%0,%1,%2,%3,%4,%5,%6,%7,%8,%9,%10,%11,%12,%13,%14,%15,%16,%17,%18,%19,%20,%21,%22,%23,%24,%25,%26,%27,%28,%29,%30,%31,%32,%33,%34,%35,%36,%37,%38,%39,%40,%41,%42,%43,%44,%45,%46,%47,%48,%49,%50,%51,%52,%53,%54,%55,%56,%57,%58,%59,%60,%61,%62,%63}, {%64,%65,%66,%67}, %68, 0, 1, 1, %69;"
   : "=f"(d[O+0]), "=f"(d[O+1]), "=f"(d[O+2]), "=f"(d[O+3]), "=f"(d[O+4]), "=f"(d[O+5]), "=f"(d[O+6]), "=f"(d[O+7]), "=f"(d[O+8]), "=f"(d[O+9]), "=f"(d[O+10]), "=f"(d[O+11]), "=f"(d[O+12]), "=f"(d[O+13]), "=f"(d[O+14]), "=f"(d[O+15]), "=f"(d[O+16]), "=f"(d[O+17]), "=f"(d[O+18]), "=f"(d[O+19]), "=f"(d[O+20]), "=f"(d[O+21]), "=f"(d[O+22]), "=f"(d[O+23]), "=f"(d[O+24]), "=f"(d[O+25]), "=f"(d[O+26]), "=f"(d[O+27]), "=f"(d[O+28]), "=f"(d[O+29]), "=f"(d[O+30]), "=f"(d[O+31]), "=f"(d[O+32]), "=f"(d[O+33]), "=f"(d[O+34]), "=f"(d[O+35]), "=f"(d[O+36]), "=f"(d[O+37]), "=f"(d[O+38]), "=f"(d[O+39]), "=f"(d[O+40]), "=f"(d[O+41]), "=f"(d[O+42]), "=f"(d[O+43]), "=f"(d[O+44]), "=f"(d[O+45]), "=f"(d[O+46]), "=f"(d[O+47]), "=f"(d[O+48]), "=f"(d[O+49]), "=f"(d[O+50]), "=f"(d[O+51]), "=f"(d[O+52]), "=f"(d[O+53]), "=f"(d[O+54]), "=f"(d[O+55]), "=f"(d[O+56]), "=f"(d[O+57]), "=f"(d[O+58]), "=f"(d[O+59]), "=f"(d[O+60]), "=f"(d[O+61]), "=f"(d[O+62]), "=f"(d[O+63])
   : "r"(a0), "r"(a1), "r"(a2), "r"(a3), "l"(db), "n"(TB));
  else asm volatile("{\n.reg .pred p;\nsetp.ne.b32 p, %70, 0;\nwgmma.mma_async.sync.aligned.m64n128k16.f32.bf16.bf16 {%0,%1,%2,%3,%4,%5,%6,%7,%8,%9,%10,%11,%12,%13,%14,%15,%16,%17,%18,%19,%20,%21,%22,%23,%24,%25,%26,%27,%28,%29,%30,%31,%32,%33,%34,%35,%36,%37,%38,%39,%40,%41,%42,%43,%44,%45,%46,%47,%48,%49,%50,%51,%52,%53,%54,%55,%56,%57,%58,%59,%60,%61,%62,%63}, {%64,%65,%66,%67}, %68, p, 1, 1, %69;\n}"
   : "+f"(d[O+0]), "+f"(d[O+1]), "+f"(d[O+2]), "+f"(d[O+3]), "+f"(d[O+4]), "+f"(d[O+5]), "+f"(d[O+6]), "+f"(d[O+7]), "+f"(d[O+8]), "+f"(d[O+9]), "+f"(d[O+10]), "+f"(d[O+11]), "+f"(d[O+12]), "+f"(d[O+13]), "+f"(d[O+14]), "+f"(d[O+15]), "+f"(d[O+16]), "+f"(d[O+17]), "+f"(d[O+18]), "+f"(d[O+19]), "+f"(d[O+20]), "+f"(d[O+21]), "+f"(d[O+22]), "+f"(d[O+23]), "+f"(d[O+24]), "+f"(d[O+25]), "+f"(d[O+26]), "+f"(d[O+27]), "+f"(d[O+28]), "+f"(d[O+29]), "+f"(d[O+30]), "+f"(d[O+31]), "+f"(d[O+32]), "+f"(d[O+33]), "+f"(d[O+34]), "+f"(d[O+35]), "+f"(d[O+36]), "+f"(d[O+37]), "+f"(d[O+38]), "+f"(d[O+39]), "+f"(d[O+40]), "+f"(d[O+41]), "+f"(d[O+42]), "+f"(d[O+43]), "+f"(d[O+44]), "+f"(d[O+45]), "+f"(d[O+46]), "+f"(d[O+47]), "+f"(d[O+48]), "+f"(d[O+49]), "+f"(d[O+50]), "+f"(d[O+51]), "+f"(d[O+52]), "+f"(d[O+53]), "+f"(d[O+54]), "+f"(d[O+55]), "+f"(d[O+56]), "+f"(d[O+57]), "+f"(d[O+58]), "+f"(d[O+59]), "+f"(d[O+60]), "+f"(d[O+61]), "+f"(d[O+62]), "+f"(d[O+63])
   : "r"(a0), "r"(a1), "r"(a2), "r"(a3), "l"(db), "n"(TB), "r"(sd));
}

#define NEARLY 0
#define XAHEAD 3
#define HEADN 6
#define WBATCH 1
#define WB 4
#define WSLEEP 20
#define XSPREAD 4
#define NOSEND 0
#define MSPLIT 3
#define PFALL 1
#define L2PF 1
#define STAG 0
#define SPACE 100
#define WPF 1
#define WAFTER 7
#define WPACE 0
#define GATE_AT 4
#define TPACE 40
#define PFMODE 0
#define MAPMODE 1
template <int V> struct IC { static constexpr int value = V; };
struct Maps { CUtensorMap x, ft, g64, u64, e, wr, wi, xs, ts, t, g32, u32, d224, o; };

constexpr int NCTA = 130;
constexpr int U = 16384;
constexpr int TB = 36864;
constexpr int OFF_RING = 8 * U, OFF_Z = 9 * U, OFF_XB = 12 * U, OFF_T = 13 * U, OFF_D = OFF_T;
constexpr int OFF_BAR = 14 * U, OFF_SP = OFF_BAR + 512, OFF_G = OFF_SP + 1024 + 128;
constexpr int SMEM_BYTES = OFF_G + 512;
constexpr int B_FX = 0, B_FA = 8, B_FT = 12, B_Z = 16, B_W = 24, B_HX = 25, B_TL = 26, B_HP = 27, B_WR = 30, B_E0 = 34;
constexpr int B_EA = 35, B_ET = 39, B_PZ = 43, B_RDY = 45, B_FE = 46;
constexpr int B_T = 50, B_XS = 51, B_G = 53, NBAR = 54;
__host__ __device__ constexpr int rslot(int n) { return n & 3; }
__host__ __device__ constexpr int rpar(int n) { return (n >> 2) & 1; }

__global__ void __cluster_dims__(2, 1, 1) __launch_bounds__(512, 1)
fused_kernel(Work* __restrict__ ws, const uint16_t* __restrict__ dtab, const __nv_bfloat16* __restrict__ w_r, const __nv_bfloat16* __restrict__ w_i,
             const __nv_bfloat16* __restrict__ gate_w, const __grid_constant__ Maps maps) {
  extern __shared__ __align__(1024) uint8_t smem[];
  const uint32_t sb = smem_u32(smem);
  const uint32_t bars = sb + OFF_BAR;
  const int tid = threadIdx.x, lane = tid & 31;
  const int warp = __shfl_sync(0xffffffffu, tid >> 5, 0);
  const bool helper = blockIdx.x >= 128;
  const int cl = (blockIdx.x >> 1) & 63, rank = blockIdx.x & 1;
  const int q4 = (cl & 1) | ((cl >> 2) & 2), rb = ((cl >> 1) & 3) | ((cl >> 4) << 2);
  const int j = 2 * q4 + rank;
  const int f_full = 448 * q4 + (rank ? 256 : 0);
  const int f_half = 448 * q4 + (rank ? 224 : 192);
  const int kg = 2 * j + (rb >> 3), tn = rb & 7;

  if (tid == 64) { PROF_EV(0); PROF_CK(40); }
  if (warp < 8) {
    asm volatile("barrier.cluster.arrive.relaxed.aligned;" ::: "memory");
    asm volatile("setmaxnreg.inc.sync.aligned.u32 192;");
    if (!helper) {
      const int wg = warp >> 2, w = warp & 3, g = lane >> 2;
      const bool elect = (tid & 127) == 0;
      float cX[32], cA[64], cB[64], cC[64], ci[64], ct[64];
      const int zero = blockIdx.x >> 16;
      uint32_t h[56], yf[16];
      const uint32_t d0 = (sb & 0x3FFFF) >> 4;
      const uint32_t dK = d0 | (1u << 16), dN = d0 | (512u << 16);
      const uint32_t dX = dK + wg * 512;
      constexpr uint32_t RING = OFF_RING >> 4;
      auto waitA = [&](int n) { mbar_wait(bars + 8 * (B_FA + rslot(n)), rpar(n)); };
      auto freeA = [&](int n) { mbar_arrive_if(elect, bars + 8 * (B_EA + rslot(n))); };
      auto nop = [] {};

      asm volatile("bar.sync 0, 384;" ::: "memory");
#pragma unroll 1
      for (int i = 0; i < 4; i++) {
        const uint64_t dx = d128(dX + i * 2048), df = d128(dK + (OFF_XB >> 4) + (i & 1) * 1024);
        mbar_wait(bars + 8 * (B_FX + 2 * i), 0);
        wg_fence();
        mma_ss64<0, 0, 2>(cX, df, dx, i);
        mma_ss64<0, 0, 1>(cX, df + 2, dx + 2);
        wg_commit(); wg_wait<1>();
        mbar_arrive_if(elect && i, bars + 8 * (B_EA + rslot(i - 1)));
        mma_ss64<0, 0, 1>(cX, df + 4, dx + 4);
        mma_ss64<0, 0, 1>(cX, df + 6, dx + 6);
        if (i == 0 && tid == 0) PROF_EV(1);
        mbar_wait(bars + 8 * (B_FX + 2 * i + 1), 0);
        wg_fence();
#pragma unroll
        for (int k = 0; k < 4; k++) mma_ss64<0, 0, 1>(cX, df + (512 + k * 2), dx + (1024 + k * 2));
        wg_commit();
        waitA(i);
        wg_fence();
        const uint64_t da = d128(dX + i * 1024), db = d128(dN + RING + i * 1024);
        mma_ss128<0, 1, 2>(cA, da, db, i);
        wg_commit(); wg_wait<1>();
        mbar_arrive_if(elect, bars + 8 * (B_FE + i));
#pragma unroll
        for (int k = 1; k < 4; k++) mma_ss128<0, 1, 1>(cA, da + k * 2, db + k * 128);
        wg_commit();
      }
      fence_regs<0, 32>(cX);
#pragma unroll
      for (int e = 0; e < 16; e++) yf[e] = pack_pin(cX[2 * e], cX[2 * e + 1]);
      if (tid == 0) { PROF_EV(2); PROF_CK(42); }
      {
        waitA(4); mbar_wait(bars + 8 * B_E0, 0);
        const uint64_t de = d128(dN + (wg ? RING : OFF_XB >> 4));
        wg_fence();
        mma_rs128<0, 1, 0>(cB, yf[0], yf[1], yf[2], yf[3], de);
        wg_commit();
        wg_wait<1>();
        freeA(3);
#pragma unroll
        for (int k = 1; k < 4; k++) mma_rs128<0, 1, 1>(cB, yf[4 * k], yf[4 * k + 1], yf[4 * k + 2], yf[4 * k + 3], de + k * 128);
        wg_commit();
      }
      bool rel = false;
      auto acquire = [&](int n) {
        rel = elect;
        if (!mbar_try(bars + 8 * (B_FA + rslot(n)), rpar(n))) { wg_wait<0>(); freeA(n - 1); rel = false; waitA(n); }
      };
      auto freeP = [&](int n) { mbar_arrive_if(rel, bars + 8 * (B_EA + rslot(n - 1))); };
      auto ffn_step = [&](auto first, auto split, float (&acc)[64], int n, int kb, auto done, auto work) {
        constexpr int SPLIT = decltype(split)::value;
        acquire(n);
        wg_fence();
        const uint64_t dx = d128(dX + kb * 1024), db = d128(dN + RING + rslot(n) * 1024);
        mma_ss128<0, 1, decltype(first)::value>(acc, dx, db, kb);
#pragma unroll
        for (int k = 1; k < SPLIT; k++) mma_ss128<0, 1, 1>(acc, dx + k * 2, db + k * 128);
        wg_commit();
        work();
        wg_wait<1>();
        freeP(n);
        done();
        if (SPLIT < 4) {
          wg_fence();
#pragma unroll
          for (int k = SPLIT; k < 4; k++) mma_ss128<0, 1, 1>(acc, dx + k * 2, db + k * 128);
          wg_commit();
        }
      };
      {
        const int s0 = 2 * rb + wg, kr = 2 * ((s0 & 1) | ((s0 & 4) >> 1));
        const int m = lane >> 3, r = lane & 7;
        const uint32_t a0 = sb + OFF_XB + wg * 8192 + (((w >> 1) * 8 + (m >> 1)) * 2 + (w & 1)) * 256 + (m & 1) * 128 + ((r ^ (kr + (m & 1))) << 4);
        ffn_step(IC<1>(), IC<4>(), cA, 5, 4, [&] { fence_regs<0, 64>(cB); }, nop);
        asm volatile("bar.sync 5, 256;" ::: "memory");
        auto stage = [&](int i) {
          stsm4t(a0 + i * 1024, pack_bf16(cB[8 * i] - cB[34 + 8 * i], cB[8 * i + 1] - cB[35 + 8 * i]),
                 pack_bf16(cB[32 + 8 * i] + cB[8 * i + 2], cB[33 + 8 * i] + cB[8 * i + 3]),
                 pack_bf16(cB[8 * i + 4] - cB[38 + 8 * i], cB[8 * i + 5] - cB[39 + 8 * i]),
                 pack_bf16(cB[36 + 8 * i] + cB[8 * i + 6], cB[37 + 8 * i] + cB[8 * i + 7]));
          if (j == 0 && w == 0) {
            const uint32_t a1 = r ? sb + OFF_SP + 1024 : sb + OFF_SP + wg * 512 + (m & 1) * 256 + (m >> 1) * 128;
#pragma unroll
            for (int n = 2 * i; n < 2 * i + 2; n++)
              asm volatile("stmatrix.sync.aligned.m8n8.x4.shared.b16 [%0], {%1,%2,%3,%4};" ::"r"(a1 + ((n ^ (kr + (m >> 1)) ^ r) << 4)),
                           "r"(pack_bf16(cB[4 * n], cB[4 * n + 1])), "r"(pack_bf16(cB[4 * n + 2], cB[4 * n + 3])),
                           "r"(pack_bf16(cB[32 + 4 * n], cB[33 + 4 * n])), "r"(pack_bf16(cB[34 + 4 * n], cB[35 + 4 * n])) : "memory");
          }
        };
        auto publish = [&] {
          asm volatile("fence.proxy.async.shared::cta;" ::: "memory");
          __syncwarp();
          mbar_arrive_if(lane == 0, bars + 8 * (B_XS + wg));
          if (tid == 0) PROF_EV(3);
        };
        stage(0);
        ffn_step(IC<1>(), IC<1>(), cA, 6, 5, nop, nop);
        stage(1);
        ffn_step(IC<1>(), IC<1>(), cA, 7, 6, nop, nop);
        stage(2);
        ffn_step(IC<1>(), IC<2>(), cA, 8, 7, [&] { stage(3); }, nop);
        publish();
      }
      float g0 = 0.f, g1 = 0.f;
      uint32_t tag = 0;
      auto glu = [&](auto& acc, int half, int ho, int i0, int i1) {
#pragma unroll
        for (int i = i0; i < i1; i++) {
          const float o = 1.0f - ((i & 1) ? g1 : g0);
          asm volatile("" : "+f"(acc[2 * i]), "+f"(acc[2 * i + 1]), "+f"(acc[half + 2 * i]), "+f"(acc[half + 1 + 2 * i])::"memory");
          h[ho + i] = pack_pin(fmaxf(acc[2 * i], 0.f) * acc[half + 2 * i] * o, fmaxf(acc[2 * i + 1], 0.f) * acc[half + 1 + 2 * i] * o);
        }
      };
      ffn_step(IC<2>(), IC<1>(), cB, 9, zero, nop, nop);
#pragma unroll 1
      for (int kb = 1; kb < 8; kb++)
        ffn_step(IC<1>(), IC<1>(), cB, 9 + kb, kb, nop, [&] {
          if (kb == 4 + wg) {
            mbar_wait(bars + 8 * B_G, 0);
            const uint32_t gb0 = *(const uint32_t*)(smem + OFF_G + (wg * 64 + w * 16 + g) * 4), gb1 = *(const uint32_t*)(smem + OFF_G + (wg * 64 + w * 16 + g + 8) * 4);
            tag = gb0 & 1; g0 = __uint_as_float(gb0 & ~1u); g1 = __uint_as_float(gb1 & ~1u);
            glu(cA, 32, 0, 0, 8);
          } else if (kb == 6 + wg) glu(cA, 32, 0, 8, 16);
        });
      if (tid == 0) { PROF_EV(4); PROF_CK(43); }
      ffn_step(IC<0>(), IC<1>(), cC, 17, 0, nop, nop);
#pragma unroll 1
      for (int kb = 1; kb < 8; kb++)
        ffn_step(IC<1>(), IC<1>(), cC, 17 + kb, kb, nop, [&] {
          if (kb == 1 + wg) glu(cB, 32, 16, 0, 8);
          else if (kb == 3 + wg) glu(cB, 32, 16, 8, 16);
        });
      if (tid == 0) { PROF_EV(5); PROF_CK(44); }
      auto m_step = [&](auto first, int i) {
        acquire(25 + i);
        wg_fence();
        const uint64_t dx = d128(dX + i * 2048), dm = d64(dN + RING + rslot(25 + i) * 1024);
        mma_ss64<0, 1, decltype(first)::value>(ct, dx, dm);
#pragma unroll
        for (int k = 1; k < MSPLIT; k++) mma_ss64<0, 1, 1>(ct, dx + ((k >> 2) * 1024 + (k & 3) * 2), dm + k * 64);
        wg_commit();
        wg_wait<1>();
        mbar_arrive_if(rel && i < 3, bars + 8 * (B_EA + rslot(24 + i)));
        mbar_arrive_if(elect && i, bars + 8 * (B_ET + i - 1));
        wg_fence();
#pragma unroll
        for (int k = MSPLIT; k < 8; k++) mma_ss64<0, 1, 1>(ct, dx + ((k >> 2) * 1024 + (k & 3) * 2), dm + k * 64);
        wg_commit();
      };
      auto freeT = [&](int t) { mbar_arrive_if(elect, bars + 8 * (B_ET + t)); };
      m_step(IC<0>(), 0);
#pragma unroll 1
      for (int i = 1; i < 5; i++) {
        if (i == 1 + wg) glu(cC, 32, 32, 0, 8);
        else if (i == 3 + wg) glu(cC, 32, 32, 8, 16);
        if (i < 4) m_step(IC<1>(), i);
      }
      waitA(29 + wg);
      if (tid == 0) PROF_EV(6);
      if (tid == 128) PROF_EV(27);
      mbar_wait(bars + 8 * (j == 0 ? B_T : B_TL), 0);
      if (tid == 0) { PROF_EV(7); PROF_CK(45); }
      wg_fence();
      {
        const uint64_t dt = d128(dN + (OFF_T >> 4) + wg * 512), de = d128(dK + RING + (1 + wg) * 1024);
        mma_ss64<0, 1, 0>(ci, de, dt);
        mma_ss64<32, 1, 0>(ci, de + 512, dt);
#pragma unroll
        for (int k = 1; k < 4; k++) {
          mma_ss64<0, 1, 1>(ci, de + k * 2, dt + k * 128);
          mma_ss64<32, 1, 1>(ci, de + (512 + k * 2), dt + k * 128);
        }
        wg_commit();
        wg_wait<1>();
        freeT(3);
        fence_regs<0, 32>(ct);
        glu(ct, 16, 48, 0, 8);
      }

      auto twait = [&](uint32_t bar, uint32_t par, int) { mbar_wait(bar, par); };
      const int fo = warp * 128 + lane;
      auto fetch = [&](uint4 (&pv)[4], int z) {
        twait(bars + 8 * (z < 4 ? B_Z + 2 * z + wg : B_HP + z - 4), 0, 8 + z);
        const uint8_t* src = smem + (z < 5 ? OFF_Z + z * U : (z - 5) * U) + fo * 16;
#pragma unroll
        for (int i = 0; i < 4; i++) pv[i] = *(const uint4*)(src + i * 512);
      };
      auto check = [&](uint4 (&pv)[4], int z) {
        const uint32_t t0 = (uint32_t)clock();
        while (__any_sync(0xffffffffu, ((pv[0].x ^ tag) | (pv[1].x ^ tag) | (pv[2].x ^ tag) | (pv[3].x ^ tag)) & 1)) {
#pragma unroll
          for (int i = 0; i < 4; i++) pv[i] = ld_x4(ws->part + (size_t)((rb * 8 + j) * 3 + z - 4) * 1024 + fo + i * 32);
          spin_guard(t0);
        }
#pragma unroll
        for (int i = 0; i < 4; i++) pv[i].x &= ~1u;
      };
      auto head = [&](auto off, int t, bool init) {
        constexpr int O = decltype(off)::value;
        twait(bars + 8 * (B_FT + (t & 3)), t >> 2, t);
        const uint64_t db = d128(dN + (t & 3) * (TB >> 4) + rank * 256);
        wg_fence();
        mma_rs64<O, 1, 2>(ct, h[0], h[1], h[2], h[3], db, zero + init);
#pragma unroll
        for (int k = 1; k < 6; k++) mma_rs64<O, 1, 1>(ct, h[4 * k], h[4 * k + 1], h[4 * k + 2], h[4 * k + 3], db + k * 128);
        wg_commit();
        wg_wait<1>();
      };
      auto rest = [&](auto off, int t, int z) {
        constexpr int O = decltype(off)::value, P = 32 - O;
        const uint64_t db = d128(dN + (t & 3) * (TB >> 4)), dw = db + rank * 256, dm = db + (rank ? 0 : 1536);
        wg_fence();
#pragma unroll
        for (int k = 6; k < 12; k++) mma_rs64<O, 1, 1>(ct, h[4 * k], h[4 * k + 1], h[4 * k + 2], h[4 * k + 3], dw + k * 128);
        wg_commit();
        uint4 pv[4];
        if (z >= 0) fetch(pv, z);
        wg_fence();
#pragma unroll
        for (int k = 0; k < 2; k++) mma_rs64<O, 1, 1>(ct, h[48 + 4 * k], h[49 + 4 * k], h[50 + 4 * k], h[51 + 4 * k], dm + k * 128);
#pragma unroll
        for (int k = 0; k < 4; k++) mma_rs64<O, 1, 1>(ct, yf[4 * k], yf[4 * k + 1], yf[4 * k + 2], yf[4 * k + 3], db + (14 + k) * 128);
        wg_commit();
        if (z >= 0) {
          if (z >= 4) check(pv, z);
#pragma unroll
          for (int i = 0; i < 4; i++) {
            const uint32_t a[4] = {pv[i].x, pv[i].y, pv[i].z, pv[i].w};
#pragma unroll
            for (int e = 0; e < 4; e++) { ct[P + 8 * i + 2 * e] = bf_lo(a[e]); ct[P + 8 * i + 2 * e + 1] = bf_hi(a[e]); }
          }
        }
      };
      const uint32_t peerZ = mapa(sb + OFF_Z + fo * 16, rank ^ 1), peerB = mapa(bars + 8 * (B_Z + wg), rank ^ 1);
      auto send = [&](auto off, int t) {
        constexpr int O = decltype(off)::value;
        fence_regs<O, 32>(ct);
        const bool grid = t >= 3 && t < 6;
        const int z = grid ? t - 3 : t == 6 ? 3 : t;
        uint32_t pk[16];
#pragma unroll
        for (int i = 0; i < 16; i++) pk[i] = pack_bf16(ct[O + 2 * i], ct[O + 2 * i + 1]);
        if (grid) {
          const int owner = rb * 8 + 2 * ((q4 + z + 1) & 3) + rank;
          uint4* dst = ws->part + (size_t)(owner * 3 + z) * 1024 + fo;
#pragma unroll
          for (int i = 0; i < 4; i++) st_x4(dst + i * 32, (pk[4 * i] & ~1u) | tag, pk[4 * i + 1], pk[4 * i + 2], pk[4 * i + 3]);
          __syncwarp();
          hint_add_if(lane == 0, &ws->cntP[32 * owner + z]);
        } else {
#pragma unroll
          for (int i = 0; i < 4; i++)
            asm volatile("st.async.weak.shared::cluster.mbarrier::complete_tx::bytes.v4.b32 [%0], {%1,%2,%3,%4}, [%5];" ::"r"(peerZ + z * U + i * 512),
                         "r"(pk[4 * i]), "r"(pk[4 * i + 1]), "r"(pk[4 * i + 2]), "r"(pk[4 * i + 3]), "r"(peerB + 16 * z) : "memory");
        }
      };
      asm volatile("barrier.cluster.wait.aligned;" ::: "memory");
      head(IC<0>(), 0, false);
      if (elect) asm volatile("mbarrier.arrive.shared::cluster.b64 _, [%0];" ::"r"(mapa(bars + 8 * B_RDY, rank ^ 1)) : "memory");
      mbar_arrive_if(elect, bars + 8 * (B_PZ + 1));
      fence_regs<0, 64>(ci);
#pragma unroll
      for (int i = 0; i < 16; i++) {
        const float gg = ((i & 1) ? g1 : g0) * (2.0f / (2048.0f * 512.0f));
        if (i & 2) yf[i] = pack_pin((ci[2 * i] - ci[28 + 2 * i]) * gg, (ci[2 * i + 1] - ci[29 + 2 * i]) * gg);
        else yf[i] = pack_pin((ci[2 * i] + ci[36 + 2 * i]) * gg, (ci[2 * i + 1] + ci[37 + 2 * i]) * gg);
      }
      if (tid == 0) PROF_EV(8);
      if (tid == 128) PROF_EV(28);
#pragma unroll 1
      for (int t = 0;; t += 2) {
        rest(IC<0>(), t, t - 2);
        head(IC<32>(), t + 1, t >= 2);
        mbar_arrive_if(elect && t < 6, bars + 8 * (B_ET + t));
        if (t == 0) twait(bars + 8 * B_RDY, 0, 15);
        send(IC<0>(), t);
        rest(IC<32>(), t + 1, (t & 2) ? t - 1 : -1);
        if (t == 6) break;
        head(IC<0>(), t + 2, t == 2);
        mbar_arrive_if(elect && t < 4, bars + 8 * (B_ET + t + 1));
        send(IC<32>(), t + 1);
      }
      if (tid == 0) { PROF_EV(9); PROF_CK(46); }
      if (tid == 128) PROF_EV(29);
      {
        float (&sum)[64] = ct;
        uint4 p2[4], p3[4];
        fetch(p3, 3);
        if (tid == 0) PROF_EV(25);
        fetch(p2, 6);
        if (tid == 0) PROF_EV(24);
        check(p2, 6);
#pragma unroll
        for (int i = 0; i < 4; i++) {
          const uint32_t b[4] = {p2[i].x, p2[i].y, p2[i].z, p2[i].w}, c[4] = {p3[i].x, p3[i].y, p3[i].z, p3[i].w};
#pragma unroll
          for (int e = 0; e < 4; e++) {
            sum[8 * i + 2 * e] += bf_lo(c[e]) + bf_lo(b[e]);
            sum[8 * i + 2 * e + 1] += bf_hi(c[e]) + bf_hi(b[e]);
          }
        }
        if (tid == 0) PROF_EV(14);
        wg_wait<0>();
        fence_regs<32, 32>(ct);
#pragma unroll
        for (int i = 0; i < 32; i++) sum[i] += ct[32 + i];
        const uint32_t stg = sb + OFF_T + warp * 2048;
        const int mr = (lane & 7) + ((lane >> 3) & 1) * 8, mc = lane >> 4;
#pragma unroll
        for (int i = 0; i < 4; i++) {
          const uint32_t a = stg + mr * 128 + (((2 * i + mc) ^ (mr & 7)) << 4);
          asm volatile("stmatrix.sync.aligned.m8n8.x4.shared.b16 [%0], {%1,%2,%3,%4};" ::"r"(a), "r"(pack_bf16(sum[8 * i], sum[8 * i + 1])),
                       "r"(pack_bf16(sum[8 * i + 2], sum[8 * i + 3])), "r"(pack_bf16(sum[8 * i + 4], sum[8 * i + 5])),
                       "r"(pack_bf16(sum[8 * i + 6], sum[8 * i + 7])) : "memory");
        }
        asm volatile("fence.proxy.async.shared::cta;" ::: "memory");
        __syncwarp();
        if (elect_one()) {
          asm volatile("cp.async.bulk.tensor.3d.global.shared::cta.bulk_group [%0, {%2, %3, %4}], [%1];" ::"l"(&maps.o), "r"(stg), "r"(64 * j),
                       "r"(16 * w), "r"(2 * rb + wg) : "memory");
          asm volatile("cp.async.bulk.commit_group;\ncp.async.bulk.wait_group.read 0;" ::: "memory");
        }
      }
      if (tid == 0) { PROF_EV(15); PROF_CK(41); }
      if (tid == 128) PROF_EV(30);
    }
  } else if (warp < 12) {
    asm volatile("setmaxnreg.dec.sync.aligned.u32 104;");
    asm volatile("barrier.cluster.arrive.relaxed.aligned;" ::: "memory");
    const int t = tid - 256, w = warp - 8;
    const uint32_t ep = ld_x1(&ws->epoch[blockIdx.x * 8]);
    const uint32_t tag = (ep + 1) & 1;
    auto w_issue = [&](const CUtensorMap* m) {
          if (elect_one()) { mbar_expect_tx(bars + 8 * (B_WR + w), 3072); tma4d(sb + OFF_T + w * 3072, m, bars + 8 * (B_WR + w), 16 * kg, 0, 2 * w, tn); }
          __syncwarp();
    };
    auto gate_rows = [&] {
      const int r = 16 * j + 4 * w + (lane >> 3);
      const uint4* pg = (const uint4*)gate_w + (lane & 7);
      {
        float a = 0.f;
        asm volatile("bar.sync 4, 256;" ::: "memory");
#pragma unroll 1
        for (int hf = 0; hf < 2; hf++) {
          uint4 v[4], u[4];
#pragma unroll
          for (int kb = 0; kb < 4; kb++) v[kb] = __ldg(pg + (4 * hf + kb) * 8);
          mbar_wait(bars + 8 * (B_FE + 1 + 2 * hf), 0);
          if (hf) w_issue(&maps.wr);
#pragma unroll
          for (int kb = 0; kb < 4; kb++) u[kb] = *(const uint4*)(smem + (4 * hf + kb) * U + r * 128 + (((lane ^ r) & 7) << 4));
#pragma unroll
          for (int kb = 0; kb < 4; kb++) {
            a = fmaf(bf_lo(u[kb].x), bf_lo(v[kb].x), a); a = fmaf(bf_hi(u[kb].x), bf_hi(v[kb].x), a);
            a = fmaf(bf_lo(u[kb].y), bf_lo(v[kb].y), a); a = fmaf(bf_hi(u[kb].y), bf_hi(v[kb].y), a);
            a = fmaf(bf_lo(u[kb].z), bf_lo(v[kb].z), a); a = fmaf(bf_hi(u[kb].z), bf_hi(v[kb].z), a);
            a = fmaf(bf_lo(u[kb].w), bf_lo(v[kb].w), a); a = fmaf(bf_hi(u[kb].w), bf_hi(v[kb].w), a);
          }
        }
#pragma unroll
        for (int o = 4; o; o >>= 1) a += __shfl_xor_sync(0xffffffffu, a, o);
        if ((lane & 7) == 0)
          asm volatile("st.relaxed.gpu.global.f32 [%0], %1;" ::"l"(ws->gate + rb * 128 + r), "f"(tagf(__fdividef(1.0f, 1.0f + __expf(-a)), tag)) : "memory");
        if (t == 0) PROF_EV(18);
      }
    };
    {
      const int g = lane >> 2, q = lane & 3;
      uint32_t wf[32];
      if (!helper) {
        gate_rows();
        const uint32_t wa = sb + OFF_T + w * (3072 + 4) + q * 48 + g * 2;
#pragma unroll 1
        for (int ri = 0; ri < 2; ri++) {
          mbar_wait(bars + 8 * (B_WR + w), ri);
#pragma unroll
          for (int n2 = 0; n2 < 32 / WB; n2++) {
            uint32_t v[WB];
#pragma unroll
            for (int i = 0; i < WB; i++) {
              const int e = n2 * WB + i;
              asm volatile("ld.shared.u16 %0, [%1];" : "=r"(v[i]) : "r"(wa + ((e >> 1) & 7) * 192 + (e & 1) * (1536 + 2) + (e >> 4) * 16) : "memory");
            }
#pragma unroll
            for (int i = 0; i < WB; i++) wf[n2 * WB + i] = __byte_perm(wf[n2 * WB + i], v[i], 0x5432);
            if (WSLEEP) { asm volatile("nanosleep.u32 %0;" ::"r"(WSLEEP + (v[WB - 1] >> 16)) : "memory"); }
          }
          __syncwarp();
          if (ri == 0) w_issue(&maps.wi);
        }
        asm volatile("bar.sync 1, 128;" ::: "memory");
        if (t == 0) PROF_EV(11);
      } else {
        asm volatile("bar.sync 4, 256;" ::: "memory");
        hint_wait(&ws->cntW[0], (ep + 1) * 128u);
        const uint32_t t0 = (uint32_t)clock();
#pragma unroll 1
        for (;;) {
          uint32_t bad = 0;
#pragma unroll
          for (int i = 0; i < 32; i++) {
            const float2 v = ld_x2((const float2*)ws->Wh + (i >> 4) * 2048 + 16 * w + g + 8 * (i & 1) + 64 * q + ((i >> 1) & 7) * 256);
            wf[i] = __float_as_uint(v.x); bad |= __float_as_uint(v.y) ^ tag;
          }
          if (!__any_sync(0xffffffffu, bad & 1)) break;
          spin_guard(t0);
        }
        if (t == 0) PROF_EV(11);
      }
      if (w == 0 && elect_one()) { mbar_expect_tx(bars + 8 * B_W, 8192); bulk_load(sb + OFF_D, dtab, 8192, bars + 8 * B_W); }
      mbar_wait(bars + 8 * B_W, 0);
      mbar_wait(bars + 8 * B_HX, 0);
      if (t == 0) PROF_EV(12);
      const uint32_t dd = (sb & 0x3FFFF) >> 4;
      const uint64_t dF = d128((dd + (OFF_D >> 4)) | (512u << 16)), dI = d128((dd + (OFF_D >> 4)) | (1u << 16)), dA = d128((dd + (OFF_XB >> 4)) | (512u << 16));
      float az[32];
      const int zero = blockIdx.x >> 16;
      uint32_t pf[32];
#pragma unroll
      for (int mt = 0; mt < 2; mt++) {
        wg_fence();
        if (mt == 0) mma_ss64<0, 3, 0>(az, dA, dF);
        else mma_ss64<0, 3, 2>(az, dA + 512, dF, zero);
#pragma unroll
        for (int k = 1; k < 4; k++) mma_ss64<0, 3, 1>(az, dA + (mt * 512 + k * 128), dF + k * 128);
        wg_commit();
        wg_wait<0>();
        fence_regs<0, 32>(az);
#pragma unroll
        for (int i = 0; i < 16; i++) {
          const float wr = bf_lo(wf[16 * mt + i]), wi = bf_hi(wf[16 * mt + i]);
          pf[16 * mt + i] = pack_pin(fmaf(az[2 * i], wr, -az[2 * i + 1] * wi), fmaf(az[2 * i], wi, az[2 * i + 1] * wr));
        }
      }
      if (t == 0) PROF_EV(16);
#pragma unroll
      for (int mt = 0; mt < 2; mt++) {
        wg_fence();
        mma_rs64<0, 0, 2>(az, pf[16 * mt], pf[16 * mt + 1], pf[16 * mt + 2], pf[16 * mt + 3], dI, mt ? (int)helper : zero);
#pragma unroll
        for (int k = 1; k < 4; k++) mma_rs64<0, 0, 1>(az, pf[16 * mt + 4 * k], pf[16 * mt + 4 * k + 1], pf[16 * mt + 4 * k + 2], pf[16 * mt + 4 * k + 3], dI + k * 2);
        wg_commit();
        wg_wait<0>();
        fence_regs<0, 32>(az);
        if (!helper) {
          const int m = lane >> 3, r = lane & 7;
          const int sl = 2 * (m >> 1) + ((r >> 1) & 1) + 4 * (r >> 2);
          const uint32_t a0 = sb + OFF_XB + (2 * w + (m & 1)) * 2048 + sl * 64 + (((mt * 2 + (r & 1)) ^ (sl >> 1)) << 4);
#pragma unroll
          for (int i = 0; i < 4; i++)
            stsm4t(a0 + i * 512, pack_bf16(az[8 * i], az[8 * i + 1]), pack_bf16(az[8 * i + 2], az[8 * i + 3]), pack_bf16(az[8 * i + 4], az[8 * i + 5]),
                   pack_bf16(az[8 * i + 6], az[8 * i + 7]));
        }
      }
      if (helper) {
#pragma unroll
        for (int i = 0; i < 16; i++) {
          const int n = i >> 1, s0 = 8 * (n >> 1) + 2 * (n & 1) + (q & 1) + 4 * (q >> 1);
          if ((n & 1) == (int)(blockIdx.x & 1)) st_u2(ws->Ts + s0 * 64 + 16 * w + g + 8 * (i & 1), pack_bf16(az[2 * i], az[2 * i + 1]), tag);
        }
        __syncwarp();
        hint_add_if(lane == 0, &ws->cntH[0]);
        if (t == 0) { ws->epoch[blockIdx.x * 8] = ep + 1; PROF_EV(13); }
      } else {
        asm volatile("fence.proxy.async.shared::cta;" ::: "memory");
        __syncwarp();
        if (elect_one()) {
          if (t == 0) PROF_EV(17);
          if (SPACE) __nanosleep(SPACE * w);
          asm volatile("cp.async.bulk.tensor.3d.global.shared::cta.bulk_group [%0, {%2, %3, %4}], [%1];" ::"l"(&maps.ts), "r"(sb + OFF_XB + w * 4096),
                       "r"(32 * kg), "r"(0), "r"(8 * tn + 2 * w) : "memory");
          bulk_done_signal(&ws->cntT[32 * j]);
          if (t == 96) PROF_EV(13);
        }
        __syncwarp();
        if (j == 0) {
          hint_wait(&ws->cntH[0], (ep + 1) * 8u);
          const uint32_t t0 = (uint32_t)clock();
          float2 v;
          do { v = ld_x2((const float2*)ws->Ts + 2 * rb * 64 + t); spin_guard(t0); } while (__any_sync(0xffffffffu, (__float_as_uint(v.y) ^ tag) & 1));
          mbar_wait(bars + 8 * B_TL, 0);
          const uint32_t u = __float_as_uint(v.x);
          *(uint16_t*)(smem + OFF_T + t * 128 + ((t & 7) << 4)) = (uint16_t)u;
          *(uint16_t*)(smem + OFF_T + t * 128 + (((t & 7) ^ 1) << 4)) = (uint16_t)(u >> 16);
          asm volatile("fence.proxy.async.shared::cta;" ::: "memory");
          __syncwarp();
          mbar_arrive_if(lane == 0, bars + 8 * B_T);
        }
      }
    }
  } else {
    asm volatile("setmaxnreg.dec.sync.aligned.u32 24;");
    auto xf_load = [&](int q) {
      const uint32_t fb = bars + 8 * (B_FX + q);
      mbar_expect_tx(fb, U + 8192);
      tma3d(sb + q * U, &maps.x, fb, 64 * q, 0, 2 * rb);
      if (q >= 4) mbar_wait(bars + 8 * (B_FE + ((q - 4) >> 1)), 0);
      tma2d(sb + OFF_XB + (q & 3) * 8192, &maps.ft, fb, 64 * q, 64 * j);
    };
    if (elect_one()) {
      if (warp == 14) {
#pragma unroll
        for (int i = 0; i < B_FT; i++) mbar_init(bars + 8 * i, 1);
        asm volatile("fence.mbarrier_init.release.cluster;" ::: "memory");
        if (!helper) {
#pragma unroll 1
          for (int n = 0; n < 2; n++) {
            const uint32_t fb = bars + 8 * (B_FA + n);
            xf_load(2 * n); xf_load(2 * n + 1);
            mbar_expect_tx(fb, U);
            tma2d(sb + OFF_RING + n * U, &maps.g64, fb, f_full, 64 * n);
            tma2d(sb + OFF_RING + n * U + 8192, &maps.u64, fb, f_full, 64 * n);
          }
        }
      } else if (warp == 15) {
#pragma unroll
        for (int i = B_FT; i < NBAR; i++) mbar_init(bars + 8 * i, i < B_EA ? 1 : i < B_T ? 2 : 4);
#pragma unroll
        for (int i = 0; i < 8; i++) mbar_expect_tx(bars + 8 * (B_Z + i), U / 2);
        asm volatile("fence.mbarrier_init.release.cluster;" ::: "memory");
        asm volatile("fence.proxy.async.shared::cta;" ::: "memory");
      } else if (warp == 13) {
#pragma unroll
        for (int i = 1; i < 4; i++) asm volatile("prefetch.tensormap [%0];" ::"l"((const char*)&maps + i * 128) : "memory");
      }
    }
    __syncwarp();
    asm volatile("bar.arrive 0, 384;" ::: "memory");
    asm volatile("bar.arrive 4, 256;" ::: "memory");
    __syncwarp();
    asm volatile("barrier.cluster.arrive.relaxed.aligned;" ::: "memory");
    asm volatile("bar.sync 3, 128;" ::: "memory");
    if (warp == 15 && !helper) {
        mbar_wait(bars + 8 * B_FE, 0);
        const uint32_t tag = (ld_x1(&ws->epoch[blockIdx.x * 8]) + 1) & 1;
        const int c = lane >> 4, jj = 16 * blockIdx.x + (lane & 15), jm = (2048 - jj) & 2047;
        const unsigned short* pr = (const unsigned short*)w_r + 256 * c;
        const unsigned short* pi = (const unsigned short*)w_i + 256 * c;
        const float wr = 0.25f * (bf_lo(__ldg(pr + jj * 257)) + bf_lo(__ldg(pr + jm * 257)));
        const float wi = 0.25f * (bf_lo(__ldg(pi + jj * 257)) - bf_lo(__ldg(pi + jm * 257)));
        st_u2(ws->Wh + c * 2048 + jj, c ? pack_bf16(-wi, wr) : pack_bf16(wr, wi), tag);
        __syncwarp();
        hint_add_if(lane == 0, &ws->cntW[0]);
        mbar_wait(bars + 8 * B_XS, 0);
        const uint32_t t0 = (uint32_t)clock();
        uint4 v;
        do { v = ld_x4(ws->gate + rb * 128 + 4 * lane); spin_guard(t0); } while (__any_sync(0xffffffffu, ((v.x ^ tag) | (v.y ^ tag) | (v.z ^ tag) | (v.w ^ tag)) & 1));
        *(uint4*)(smem + OFF_G + lane * 16) = v;
        __syncwarp();
        mbar_arrive_if(lane < 4, bars + 8 * B_G);
      }
    if ((!helper || warp == 15) && elect_one()) {
      if (warp < 14) {
        const int p = warp - 12;
#pragma unroll 1
        for (int i = 4 + p; i < 14; i += 2) asm volatile("prefetch.tensormap [%0];" ::"l"((const char*)&maps + i * 128) : "memory");
#pragma unroll 1
        for (int n = 2; n < 31; n++) {
          const bool table = n == 4 || n >= 29;
          const int q = n < 4 ? n : n - 1;
          const CUtensorMap* m = table ? &maps.e : n >= 25 ? &maps.g32 + p : &maps.g64 + p;
          const int c0 = table ? 0 : n >= 25 ? f_half : f_full + 64 * (q >> 3);
          const int c1 = table ? (2 * rb + ((n & 1) ^ 1)) * 128 + 64 * p : n >= 25 ? 128 * (n - 25) : 64 * (q & 7);
          const uint32_t fb = bars + 8 * (B_FA + (n & 3)), dst = sb + OFF_RING + (n & 3) * U + p * 8192;
          if (n < 4) mbar_wait(bars + 8 * (B_FE + n - 2), 0);
          else mbar_wait(bars + 8 * (B_EA + (n & 3)), ((n >> 2) & 1) ^ 1);
          tma2d(dst, m, fb, c0, c1);
          if (p == 0) mbar_expect_tx(fb, U);
        }
      } else if (warp == 15) {
        const unsigned ep1 = ld_x1(&ws->epoch[blockIdx.x * 8]) + 1;
        flag_wait(&ws->cntX[helper ? 0 : 32 * j], ep1 * 16u);
        PROF_EV(22);
        mbar_expect_tx(bars + 8 * B_HX, U);
        bulk_load(sb + OFF_XB, ws->X + (size_t)(helper ? 128 : kg * 8 + tn) * 8192, U, bars + 8 * B_HX);
        if (!helper) {
          flag_wait(&ws->cntT[32 * j], ep1 * 64u);
          PROF_EV(23);
          mbar_expect_tx(bars + 8 * B_TL, U);
          tma3d(sb + OFF_T, &maps.t, bars + 8 * B_TL, 64 * j, 0, 2 * rb);
#pragma unroll 1
          for (int i = 0; i < 3; i++) {
            flag_wait(&ws->cntP[32 * (rb * 8 + j) + i], ep1 * 8u);
            mbar_wait(bars + 8 * (B_PZ + (i == 0)), 0);
            if (i == 2) PROF_EV(26);
            mbar_expect_tx(bars + 8 * (B_HP + i), U);
            bulk_load(sb + (i ? (i - 1) * U : OFF_T), ws->part + (size_t)((rb * 8 + j) * 3 + i) * 1024, U, bars + 8 * (B_HP + i));
          }
          ws->epoch[blockIdx.x * 8] = ep1;
        }
      } else {
#pragma unroll 1
        for (int q = 4; q < 8; q++) xf_load(q);
        mbar_wait(bars + 8 * (B_FE + 2), 0);
        mbar_expect_tx(bars + 8 * B_E0, U);
        tma2d(sb + OFF_XB, &maps.e, bars + 8 * B_E0, 0, 2 * rb * 128);
        tma2d(sb + OFF_XB + 8192, &maps.e, bars + 8 * B_E0, 0, 2 * rb * 128 + 64);
#pragma unroll 1
        for (int h2 = 0; h2 < 2; h2++) {
          const int s0 = 2 * rb + h2, sg = (s0 & ~6) | ((s0 & 2) << 1) | ((s0 & 4) >> 1);
          mbar_wait(bars + 8 * (B_XS + h2), 0);
#pragma unroll 1
          for (int c = 0; c < 2; c++) {
            asm volatile("cp.async.bulk.tensor.4d.global.shared::cta.bulk_group [%0, {%2, %3, %4, %5}], [%1];" ::"l"(&maps.xs),
                         "r"(sb + OFF_XB + h2 * 8192 + c * 4096), "r"(0), "r"(sg), "r"(0), "r"(16 * j + 8 * c) : "memory");
            if (j == 0)
              asm volatile("cp.async.bulk.global.shared::cta.bulk_group [%0], [%1], 256;" ::"l"(ws->X + 128 * 8192 + c * 4096 + sg * 128),
                           "r"(sb + OFF_SP + h2 * 512 + c * 256) : "memory");
            if (SPACE && h2 + c < 2) __nanosleep(SPACE);
          }
        }
        bulk_done_signal(&ws->cntX[32 * j]);
        PROF_EV(20);
        if (rb < 8) asm volatile("cp.async.bulk.prefetch.tensor.2d.L2.global [%0, {%1, %2}];" ::"l"(&maps.g32 + (rb >> 2)), "r"(f_half), "r"(128 * (rb & 3)) : "memory");
        else asm volatile("cp.async.bulk.prefetch.tensor.2d.L2.global [%0, {%1, %2}];" ::"l"(&maps.d224), "r"(64 * (rb - 8)), "r"(224 * j) : "memory");
#pragma unroll 1
        for (int t = 0; t < 8; t++) {
          const int i = t < 3 ? t + 1 : t < 6 ? t - 2 : 0;
          const int col = 64 * (2 * ((q4 + i) & 3) + ((t < 3 || t == 6) ? 1 - rank : rank));
          const uint32_t fb = bars + 8 * (B_FT + (t & 3)), dst = sb + (t & 3) * TB;
          mbar_wait(bars + 8 * (B_ET + (t == 2 ? 3 : t & 3)), t >> 2);
          mbar_expect_tx(fb, TB);
          tma2d(dst, &maps.d224, fb, col, 224 * j);
          if (t < 2) mbar_wait(bars + 8 * (B_ET + t + 1), 0);
          tma2d(dst + 28672, &maps.ft, fb, col, 64 * j);
        }
      }
    }
  }
}

typedef CUresult (*EncodeFn)(CUtensorMap*, CUtensorMapDataType, cuuint32_t, void*, const cuuint64_t*, const cuuint64_t*, const cuuint32_t*,
                             const cuuint32_t*, CUtensorMapInterleave, CUtensorMapSwizzle, CUtensorMapL2promotion, CUtensorMapFloatOOBfill);

static void encode(EncodeFn f, CUtensorMap* m, const void* base, int rank, const cuuint64_t* dims, const cuuint64_t* strides, const cuuint32_t* box,
                   CUtensorMapSwizzle sw) {
  cuuint32_t es[5] = {1, 1, 1, 1, 1};
  f(m, CU_TENSOR_MAP_DATA_TYPE_BFLOAT16, rank, (void*)base, dims, strides, box, es, CU_TENSOR_MAP_INTERLEAVE_NONE, sw,
    CU_TENSOR_MAP_L2_PROMOTION_L2_128B, CU_TENSOR_MAP_FLOAT_OOB_FILL_NONE);
}

extern "C" void kernel_launch(void* const* d_in, const int* in_sizes, int n_in, void* d_out, int out_size) {
  (void)in_sizes; (void)n_in; (void)out_size;
  const __nv_bfloat16* x = (const __nv_bfloat16*)d_in[0];
  const __nv_bfloat16* w_r = (const __nv_bfloat16*)d_in[1];
  const __nv_bfloat16* w_i = (const __nv_bfloat16*)d_in[2];
  const __nv_bfloat16* Wg = (const __nv_bfloat16*)d_in[4];
  const __nv_bfloat16* Wu = (const __nv_bfloat16*)d_in[5];
  const __nv_bfloat16* Wd = (const __nv_bfloat16*)d_in[6];
  const __nv_bfloat16* gw = (const __nv_bfloat16*)d_in[7];

  void* fp = nullptr; cudaDriverEntryPointQueryResult qr;
  cudaGetDriverEntryPoint("cuTensorMapEncodeTiled", &fp, cudaEnableDefault, &qr);
  EncodeFn enc = (EncodeFn)fp;
  void *pFT, *pET, *pDT, *pW;
  cudaGetSymbolAddress(&pDT, g_DT); cudaGetSymbolAddress(&pW, g_work);
  void *pX = ((Work*)pW)->X, *pT = ((Work*)pW)->T;
  cudaGetSymbolAddress(&pFT, g_FT); cudaGetSymbolAddress(&pET, g_ET);

  Maps mp;
  const CUtensorMapSwizzle S128 = CU_TENSOR_MAP_SWIZZLE_128B, S64 = CU_TENSOR_MAP_SWIZZLE_64B;
  { cuuint64_t d[3] = {512, 64, 32}, s[2] = {32768, 1024}; cuuint32_t b[3] = {64, 64, 2}, b2[3] = {64, 16, 1};
    encode(enc, &mp.x, x, 3, d, s, b, S128); encode(enc, &mp.o, d_out, 3, d, s, b2, S128); }
  { cuuint64_t d[2] = {512, 512}, s[1] = {1024}; cuuint32_t b[2] = {64, 64}; encode(enc, &mp.ft, pFT, 2, d, s, b, S128); }
  { cuuint64_t d[4] = {128, 32, 2, 129}, s[3] = {256, 8192, 16384}; cuuint32_t b[4] = {128, 1, 2, 8}; encode(enc, &mp.xs, pX, 4, d, s, b, CU_TENSOR_MAP_SWIZZLE_NONE); }
  { cuuint64_t d[3] = {512, 32, 64}, s[2] = {65536, 1024}; cuuint32_t b[3] = {32, 32, 2}; encode(enc, &mp.ts, pT, 3, d, s, b, S64); }
  { cuuint64_t d[3] = {512, 64, 32}, s[2] = {1024, 65536}; cuuint32_t b[3] = {64, 64, 2}; encode(enc, &mp.t, pT, 3, d, s, b, S128); }
  { cuuint64_t d[2] = {64, 4096}, s[1] = {128}; cuuint32_t b[2] = {64, 64}; encode(enc, &mp.e, pET, 2, d, s, b, S128); }
  { cuuint64_t d[2] = {1792, 512}, s[1] = {3584}; cuuint32_t b[2] = {64, 64}, b2[2] = {32, 128};
    encode(enc, &mp.g64, Wg, 2, d, s, b, S128); encode(enc, &mp.u64, Wu, 2, d, s, b, S128);
    encode(enc, &mp.g32, Wg, 2, d, s, b2, S64); encode(enc, &mp.u32, Wu, 2, d, s, b2, S64); }
  { cuuint64_t d[2] = {512, 1792}, s[1] = {1024}; cuuint32_t b[2] = {64, 224}; encode(enc, &mp.d224, Wd, 2, d, s, b, S128); }
  { cuuint64_t d[4] = {264, 32, 8, 8}, s[3] = {32896, 512, 4112}; cuuint32_t b[4] = {24, 32, 2, 1};
    encode(enc, &mp.wr, w_r, 4, d, s, b, CU_TENSOR_MAP_SWIZZLE_NONE); encode(enc, &mp.wi, w_i, 4, d, s, b, CU_TENSOR_MAP_SWIZZLE_NONE); }

  cudaFuncSetAttribute(fused_kernel, cudaFuncAttributeMaxDynamicSharedMemorySize, SMEM_BYTES);
  fused_kernel<<<NCTA, 512, SMEM_BYTES>>>((Work*)pW, (const uint16_t*)pDT, w_r, w_i, gw, mp);
}
```

```cpp
#include <cuda_runtime.h>
#include <cuda_bf16.h>
#include <cuda.h>
#include <stdint.h>

namespace tbl {
constexpr double PI = 3.14159265358979323846264338327950288;
constexpr double sin_s(double x) { double t = x, s = x; for (int n = 1; n < 12; n++) { t *= -x * x / ((2 * n) * (2 * n + 1)); s += t; } return s; }
constexpr double cos_s(double x) { double t = 1, s = 1; for (int n = 1; n < 12; n++) { t *= -x * x / ((2 * n - 1) * (2 * n)); s += t; } return s; }
constexpr double cos2048(int m) {
  m &= 2047; if (m > 1024) m = 2048 - m;
  bool neg = false; if (m > 512) { m = 1024 - m; neg = true; }
  double v = (m <= 256) ? cos_s(2 * PI * m / 2048) : sin_s(2 * PI * (512 - m) / 2048);
  return neg ? -v : v;
}
constexpr uint16_t to_bf16(double v) {
  if (v == 0) return 0;
  uint16_t s = 0; if (v < 0) { s = 0x8000; v = -v; }
  int e = 0; while (v >= 2) { v /= 2; e++; } while (v < 1) { v *= 2; e--; }
  double m = (v - 1) * 128; int mi = (int)m; double fr = m - mi;
  if (fr > 0.5 || (fr == 0.5 && (mi & 1))) mi++;
  if (mi == 128) { mi = 0; e++; }
  return (uint16_t)(s | ((e + 127) << 7) | mi);
}
struct CosT { uint16_t v[2048]; constexpr CosT() : v() { for (int i = 0; i < 2048; i++) v[i] = to_bf16(cos2048(i)); } };
struct alignas(1024) FT {
  uint16_t v[512 * 512];
  constexpr FT() : v() {
    CosT c;
    for (int r = 0; r < 512; r++) {
      int k = (r >> 4) * 8 + (r & 7), e = (r >> 3) & 1;
      int mul = 4 * k, add = e ? 512 : 0;
      if (k == 0 && e == 1) { mul = 1024; add = 0; }
      for (int d = 0; d < 512; d++) v[r * 512 + d] = c.v[(d * mul + add) & 2047];
    }
  }
};
struct alignas(1024) ET {
  uint16_t v[2048 * 128];
  constexpr ET() : v() {
    CosT c;
    for (int s = 0; s < 2048; s++)
      for (int j = 0; j < 64; j++) {
        const int o = (s & 31) * 8192 + (s >> 5) * 64 + j;
        v[o] = c.v[(s * j) & 2047]; v[o + 4096] = c.v[(s * j + 512) & 2047];
      }
  }
};
struct alignas(1024) DT {
  uint16_t v[64 * 64];
  constexpr DT() : v() {
    CosT c;
    for (int r = 0; r < 64; r++)
      for (int n = 0; n < 64; n++) {
        const int sg = r >> 1, s0 = (sg & ~6) | ((sg & 2) << 1) | ((sg & 4) >> 1), e = r & 1, f = n & 1;
        const int m = 64 * s0 * (n >> 1) + (e == f ? 0 : e ? -512 : 512);
        v[r * 64 + (((n >> 3) ^ (r & 7)) << 3) + (n & 7)] = c.v[m & 2047];
      }
  }
};
}

__device__ constexpr tbl::FT g_FT = tbl::FT();
__device__ constexpr tbl::ET g_ET = tbl::ET();
__device__ constexpr tbl::DT g_DT = tbl::DT();

struct alignas(1024) Work {
  unsigned epoch[132 * 8];
  unsigned cntX[8 * 32], cntT[8 * 32], cntP[128 * 32], cntW[32], cntH[32];
  alignas(16) float gate[16 * 128];
  alignas(16) uint2 Wh[2 * 2048];
  alignas(16) uint2 Ts[32 * 64];
  alignas(1024) uint16_t X[129 * 8192];
  alignas(1024) uint16_t T[32 * 64 * 512];
  alignas(1024) uint4 part[128 * 3 * 1024];
};
__device__ Work g_work;
#define PROF_EV(i) do {} while (0)
#define PROF_CK(i) do {} while (0)

__device__ __forceinline__ uint32_t smem_u32(const void* p) { return (uint32_t)__cvta_generic_to_shared(p); }
__device__ __forceinline__ void mbar_init(uint32_t bar, uint32_t cnt) { asm volatile("mbarrier.init.shared::cta.b64 [%0], %1;" ::"r"(bar), "r"(cnt)); }
__device__ __forceinline__ void mbar_expect_tx(uint32_t bar, uint32_t bytes) { asm volatile("mbarrier.arrive.expect_tx.shared::cta.b64 _, [%0], %1;" ::"r"(bar), "r"(bytes) : "memory"); }
__device__ __forceinline__ void mbar_arrive(uint32_t bar) { asm volatile("mbarrier.arrive.shared::cta.b64 _, [%0];" ::"r"(bar) : "memory"); }
__device__ __forceinline__ bool elect_one() {
  uint32_t p;
  asm volatile("{\n.reg .pred p;\nelect.sync _|p, 0xffffffff;\nselp.u32 %0, 1, 0, p;\n}" : "=r"(p));
  return p;
}
__device__ __forceinline__ void mbar_arrive_if(bool p, uint32_t bar) {
  asm volatile("{\n.reg .pred p;\nsetp.ne.b32 p, %1, 0;\n@p mbarrier.arrive.shared::cta.b64 _, [%0];\n}" ::"r"(bar), "r"((int)p) : "memory");
}
__device__ __forceinline__ void hint_add_if(bool p, unsigned* a) {
  asm volatile("{\n.reg .pred p;\nsetp.ne.b32 p, %1, 0;\n@p red.relaxed.gpu.global.add.u32 [%0], 1;\n}" ::"l"(a), "r"((int)p) : "memory");
}
__device__ __forceinline__ bool mbar_try(uint32_t bar, uint32_t parity) {
  uint32_t ok;
  asm volatile("{\n.reg .pred p;\nmbarrier.test_wait.parity.shared::cta.b64 p, [%1], %2;\nselp.u32 %0, 1, 0, p;\n}" : "=r"(ok) : "r"(bar), "r"(parity) : "memory");
  return ok;
}
__device__ __forceinline__ void mbar_wait(uint32_t bar, uint32_t parity) {
  asm volatile(
      "{\n.reg .pred p;\n.reg .u32 n;\nmov.u32 n, 0;\n"
      "W_LOOP:\nmbarrier.try_wait.parity.shared::cta.b64 p, [%0], %1;\n@p bra W_DONE;\n"
      "add.u32 n, n, 1;\nsetp.lt.u32 p, n, 0x40000;\n@p bra W_LOOP;\ntrap;\nW_DONE:\n}" ::"r"(bar), "r"(parity) : "memory");
}
__device__ __forceinline__ void bulk_load(uint32_t dst, const void* src, uint32_t bytes, uint32_t bar) {
  asm volatile("cp.async.bulk.shared::cluster.global.mbarrier::complete_tx::bytes [%0], [%1], %2, [%3];" ::"r"(dst), "l"(src), "r"(bytes), "r"(bar) : "memory");
}
__device__ __forceinline__ void cp16(uint32_t dst, const void* src) { asm volatile("cp.async.cg.shared.global [%0], [%1], 16;" ::"r"(dst), "l"(src) : "memory"); }
__device__ __forceinline__ void spin_guard(uint32_t t0) { if ((uint32_t)clock() - t0 > (1u << 30)) __trap(); }
__device__ __forceinline__ float tagf(float v, uint32_t tag) { return __uint_as_float((__float_as_uint(v) & ~1u) | tag); }
__device__ __forceinline__ float untag(float v) { return __uint_as_float(__float_as_uint(v) & ~1u); }
__device__ __forceinline__ void st_x2(float2* p, float a, float b) { asm volatile("st.relaxed.gpu.global.v2.f32 [%0], {%1,%2};" ::"l"(p), "f"(a), "f"(b) : "memory"); }
__device__ __forceinline__ float2 ld_x2(const float2* p) { float2 v; asm volatile("ld.relaxed.gpu.global.v2.f32 {%0,%1}, [%2];" : "=f"(v.x), "=f"(v.y) : "l"(p) : "memory"); return v; }
__device__ __forceinline__ void st_u2(uint2* p, uint32_t a, uint32_t b) { asm volatile("st.relaxed.gpu.global.v2.u32 [%0], {%1,%2};" ::"l"(p), "r"(a), "r"(b) : "memory"); }
__device__ __forceinline__ void prefetch2d(const CUtensorMap* m, int c0, int c1) { asm volatile("cp.async.bulk.prefetch.tensor.2d.L2.global [%0, {%1, %2}];" ::"l"(m), "r"(c0), "r"(c1) : "memory"); }
__device__ __forceinline__ void prefetch1d(const void* p, uint32_t bytes) { asm volatile("cp.async.bulk.prefetch.L2.global [%0], %1;" ::"l"(p), "r"(bytes) : "memory"); }
__device__ __forceinline__ uint32_t ld_x1(const void* p) { uint32_t v; asm volatile("ld.relaxed.gpu.global.u32 %0, [%1];" : "=r"(v) : "l"(p) : "memory"); return v; }
__device__ __forceinline__ uint4 ld_x4(const void* p) { uint4 v; asm volatile("ld.relaxed.gpu.global.v4.u32 {%0,%1,%2,%3}, [%4];" : "=r"(v.x), "=r"(v.y), "=r"(v.z), "=r"(v.w) : "l"(p) : "memory"); return v; }
__device__ __forceinline__ void st_x4(void* p, uint32_t a, uint32_t b, uint32_t c, uint32_t d) { asm volatile("st.relaxed.gpu.global.v4.u32 [%0], {%1,%2,%3,%4};" ::"l"(p), "r"(a), "r"(b), "r"(c), "r"(d) : "memory"); }
__device__ __forceinline__ uint32_t mapa(uint32_t a, uint32_t cta) { uint32_t r; asm volatile("mapa.shared::cluster.u32 %0, %1, %2;" : "=r"(r) : "r"(a), "r"(cta)); return r; }
__device__ __forceinline__ void stsm4t(uint32_t a, uint32_t r0, uint32_t r1, uint32_t r2, uint32_t r3) {
  asm volatile("stmatrix.sync.aligned.m8n8.x4.trans.shared.b16 [%0], {%1,%2,%3,%4};" ::"r"(a), "r"(r0), "r"(r1), "r"(r2), "r"(r3) : "memory");
}
__device__ __forceinline__ void hint_add(unsigned* p) { asm volatile("red.relaxed.gpu.global.add.u32 [%0], 1;" ::"l"(p) : "memory"); }
__device__ __forceinline__ void hint_wait(const unsigned* p, unsigned target) {
  const uint32_t t0 = (uint32_t)clock();
  while ((int)(ld_x1(p) - target) < 0) spin_guard(t0);
}
__device__ __forceinline__ void bulk_done_signal(unsigned* p) {
  asm volatile("cp.async.bulk.commit_group;\ncp.async.bulk.wait_group 0;\nfence.proxy.async.global;" ::: "memory");
  hint_add(p);
}
__device__ __forceinline__ void flag_wait(const unsigned* p, unsigned target) {
  hint_wait(p, target);
  asm volatile("fence.proxy.async.global;" ::: "memory");
}
__device__ __forceinline__ void tma2d(uint32_t dst, const CUtensorMap* m, uint32_t bar, int c0, int c1) {
  asm volatile("cp.async.bulk.tensor.2d.shared::cluster.global.mbarrier::complete_tx::bytes [%0], [%1, {%3, %4}], [%2];" ::"r"(dst), "l"(m), "r"(bar), "r"(c0), "r"(c1) : "memory");
}
__device__ __forceinline__ void tma3d(uint32_t dst, const CUtensorMap* m, uint32_t bar, int c0, int c1, int c2) {
  asm volatile("cp.async.bulk.tensor.3d.shared::cluster.global.mbarrier::complete_tx::bytes [%0], [%1, {%3, %4, %5}], [%2];" ::"r"(dst), "l"(m), "r"(bar), "r"(c0), "r"(c1), "r"(c2) : "memory");
}
__device__ __forceinline__ void tma4d(uint32_t dst, const CUtensorMap* m, uint32_t bar, int c0, int c1, int c2, int c3) {
  asm volatile("cp.async.bulk.tensor.4d.shared::cluster.global.mbarrier::complete_tx::bytes [%0], [%1, {%3, %4, %5, %6}], [%2];" ::"r"(dst), "l"(m), "r"(bar), "r"(c0), "r"(c1), "r"(c2), "r"(c3) : "memory");
}
__device__ __forceinline__ void wg_fence() { asm volatile("wgmma.fence.sync.aligned;" ::: "memory"); }
__device__ __forceinline__ void wg_commit() { asm volatile("wgmma.commit_group.sync.aligned;" ::: "memory"); }
template <int N> __device__ __forceinline__ void wg_wait() { asm volatile("wgmma.wait_group.sync.aligned %0;" ::"n"(N) : "memory"); }
template <int O, int N, int NN> __device__ __forceinline__ void fence_regs(float (&d)[NN]) {
#pragma unroll
  for (int i = 0; i < N; i++) asm volatile("" : "+f"(d[O + i])::"memory");
}
__device__ __forceinline__ uint32_t pack_bf16(float lo, float hi) {
  uint32_t r; asm("cvt.rn.bf16x2.f32 %0, %1, %2;" : "=r"(r) : "f"(hi), "f"(lo)); return r;
}
__device__ __forceinline__ uint32_t pack_pin(float lo, float hi) {
  uint32_t r; asm volatile("cvt.rn.bf16x2.f32 %0, %1, %2;" : "=r"(r) : "f"(hi), "f"(lo) : "memory"); return r;
}
__device__ __forceinline__ float bf_lo(uint32_t u) { return __uint_as_float(u << 16); }
__device__ __forceinline__ float bf_hi(uint32_t u) { return __uint_as_float(u & 0xffff0000u); }

__device__ __forceinline__ uint64_t d128(uint32_t lo) { uint64_t d; asm("mov.b64 %0, {%1, 0x40000040};" : "=l"(d) : "r"(lo)); return d; }
__device__ __forceinline__ uint64_t d64(uint32_t lo) { uint64_t d; asm("mov.b64 %0, {%1, 0x80000020};" : "=l"(d) : "r"(lo)); return d; }
template<int O,int TB,int ACC,int NN> __device__ __forceinline__ void mma_ss64(float (&d)[NN], uint64_t da, uint64_t db, int sd = 0){
  if constexpr (ACC == 1) asm volatile("wgmma.mma_async.sync.aligned.m64n64k16.f32.bf16.bf16 {%0,%1,%2,%3,%4,%5,%6,%7,%8,%9,%10,%11,%12,%13,%14,%15,%16,%17,%18,%19,%20,%21,%22,%23,%24,%25,%26,%27,%28,%29,%30,%31}, %32, %33, 1, 1, 1, %35, %34;"
   : "+f"(d[O+0]), "+f"(d[O+1]), "+f"(d[O+2]), "+f"(d[O+3]), "+f"(d[O+4]), "+f"(d[O+5]), "+f"(d[O+6]), "+f"(d[O+7]), "+f"(d[O+8]), "+f"(d[O+9]), "+f"(d[O+10]), "+f"(d[O+11]), "+f"(d[O+12]), "+f"(d[O+13]), "+f"(d[O+14]), "+f"(d[O+15]), "+f"(d[O+16]), "+f"(d[O+17]), "+f"(d[O+18]), "+f"(d[O+19]), "+f"(d[O+20]), "+f"(d[O+21]), "+f"(d[O+22]), "+f"(d[O+23]), "+f"(d[O+24]), "+f"(d[O+25]), "+f"(d[O+26]), "+f"(d[O+27]), "+f"(d[O+28]), "+f"(d[O+29]), "+f"(d[O+30]), "+f"(d[O+31])
   : "l"(da), "l"(db), "n"(TB & 1), "n"(TB >> 1));
  else if constexpr (ACC == 0) asm volatile("wgmma.mma_async.sync.aligned.m64n64k16.f32.bf16.bf16 {%0,%1,%2,%3,%4,%5,%6,%7,%8,%9,%10,%11,%12,%13,%14,%15,%16,%17,%18,%19,%20,%21,%22,%23,%24,%25,%26,%27,%28,%29,%30,%31}, %32, %33, 0, 1, 1, %35, %34;"
   : "=f"(d[O+0]), "=f"(d[O+1]), "=f"(d[O+2]), "=f"(d[O+3]), "=f"(d[O+4]), "=f"(d[O+5]), "=f"(d[O+6]), "=f"(d[O+7]), "=f"(d[O+8]), "=f"(d[O+9]), "=f"(d[O+10]), "=f"(d[O+11]), "=f"(d[O+12]), "=f"(d[O+13]), "=f"(d[O+14]), "=f"(d[O+15]), "=f"(d[O+16]), "=f"(d[O+17]), "=f"(d[O+18]), "=f"(d[O+19]), "=f"(d[O+20]), "=f"(d[O+21]), "=f"(d[O+22]), "=f"(d[O+23]), "=f"(d[O+24]), "=f"(d[O+25]), "=f"(d[O+26]), "=f"(d[O+27]), "=f"(d[O+28]), "=f"(d[O+29]), "=f"(d[O+30]), "=f"(d[O+31])
   : "l"(da), "l"(db), "n"(TB & 1), "n"(TB >> 1));
  else asm volatile("{\n.reg .pred p;\nsetp.ne.b32 p, %36, 0;\nwgmma.mma_async.sync.aligned.m64n64k16.f32.bf16.bf16 {%0,%1,%2,%3,%4,%5,%6,%7,%8,%9,%10,%11,%12,%13,%14,%15,%16,%17,%18,%19,%20,%21,%22,%23,%24,%25,%26,%27,%28,%29,%30,%31}, %32, %33, p, 1, 1, %35, %34;\n}"
   : "+f"(d[O+0]), "+f"(d[O+1]), "+f"(d[O+2]), "+f"(d[O+3]), "+f"(d[O+4]), "+f"(d[O+5]), "+f"(d[O+6]), "+f"(d[O+7]), "+f"(d[O+8]), "+f"(d[O+9]), "+f"(d[O+10]), "+f"(d[O+11]), "+f"(d[O+12]), "+f"(d[O+13]), "+f"(d[O+14]), "+f"(d[O+15]), "+f"(d[O+16]), "+f"(d[O+17]), "+f"(d[O+18]), "+f"(d[O+19]), "+f"(d[O+20]), "+f"(d[O+21]), "+f"(d[O+22]), "+f"(d[O+23]), "+f"(d[O+24]), "+f"(d[O+25]), "+f"(d[O+26]), "+f"(d[O+27]), "+f"(d[O+28]), "+f"(d[O+29]), "+f"(d[O+30]), "+f"(d[O+31])
   : "l"(da), "l"(db), "n"(TB & 1), "n"(TB >> 1), "r"(sd));
}
template<int O,int TB,int ACC,int NN> __device__ __forceinline__ void mma_rs64(float (&d)[NN], uint32_t a0, uint32_t a1, uint32_t a2, uint32_t a3, uint64_t db, int sd = 0){
  if constexpr (ACC == 1) asm volatile("wgmma.mma_async.sync.aligned.m64n64k16.f32.bf16.bf16 {%0,%1,%2,%3,%4,%5,%6,%7,%8,%9,%10,%11,%12,%13,%14,%15,%16,%17,%18,%19,%20,%21,%22,%23,%24,%25,%26,%27,%28,%29,%30,%31}, {%32,%33,%34,%35}, %36, 1, 1, 1, %37;"
   : "+f"(d[O+0]), "+f"(d[O+1]), "+f"(d[O+2]), "+f"(d[O+3]), "+f"(d[O+4]), "+f"(d[O+5]), "+f"(d[O+6]), "+f"(d[O+7]), "+f"(d[O+8]), "+f"(d[O+9]), "+f"(d[O+10]), "+f"(d[O+11]), "+f"(d[O+12]), "+f"(d[O+13]), "+f"(d[O+14]), "+f"(d[O+15]), "+f"(d[O+16]), "+f"(d[O+17]), "+f"(d[O+18]), "+f"(d[O+19]), "+f"(d[O+20]), "+f"(d[O+21]), "+f"(d[O+22]), "+f"(d[O+23]), "+f"(d[O+24]), "+f"(d[O+25]), "+f"(d[O+26]), "+f"(d[O+27]), "+f"(d[O+28]), "+f"(d[O+29]), "+f"(d[O+30]), "+f"(d[O+31])
   : "r"(a0), "r"(a1), "r"(a2), "r"(a3), "l"(db), "n"(TB));
  else if constexpr (ACC == 0) asm volatile("wgmma.mma_async.sync.aligned.m64n64k16.f32.bf16.bf16 {%0,%1,%2,%3,%4,%5,%6,%7,%8,%9,%10,%11,%12,%13,%14,%15,%16,%17,%18,%19,%20,%21,%22,%23,%24,%25,%26,%27,%28,%29,%30,%31}, {%32,%33,%34,%35}, %36, 0, 1, 1, %37;"
   : "=f"(d[O+0]), "=f"(d[O+1]), "=f"(d[O+2]), "=f"(d[O+3]), "=f"(d[O+4]), "=f"(d[O+5]), "=f"(d[O+6]), "=f"(d[O+7]), "=f"(d[O+8]), "=f"(d[O+9]), "=f"(d[O+10]), "=f"(d[O+11]), "=f"(d[O+12]), "=f"(d[O+13]), "=f"(d[O+14]), "=f"(d[O+15]), "=f"(d[O+16]), "=f"(d[O+17]), "=f"(d[O+18]), "=f"(d[O+19]), "=f"(d[O+20]), "=f"(d[O+21]), "=f"(d[O+22]), "=f"(d[O+23]), "=f"(d[O+24]), "=f"(d[O+25]), "=f"(d[O+26]), "=f"(d[O+27]), "=f"(d[O+28]), "=f"(d[O+29]), "=f"(d[O+30]), "=f"(d[O+31])
   : "r"(a0), "r"(a1), "r"(a2), "r"(a3), "l"(db), "n"(TB));
  else asm volatile("{\n.reg .pred p;\nsetp.ne.b32 p, %38, 0;\nwgmma.mma_async.sync.aligned.m64n64k16.f32.bf16.bf16 {%0,%1,%2,%3,%4,%5,%6,%7,%8,%9,%10,%11,%12,%13,%14,%15,%16,%17,%18,%19,%20,%21,%22,%23,%24,%25,%26,%27,%28,%29,%30,%31}, {%32,%33,%34,%35}, %36, p, 1, 1, %37;\n}"
   : "+f"(d[O+0]), "+f"(d[O+1]), "+f"(d[O+2]), "+f"(d[O+3]), "+f"(d[O+4]), "+f"(d[O+5]), "+f"(d[O+6]), "+f"(d[O+7]), "+f"(d[O+8]), "+f"(d[O+9]), "+f"(d[O+10]), "+f"(d[O+11]), "+f"(d[O+12]), "+f"(d[O+13]), "+f"(d[O+14]), "+f"(d[O+15]), "+f"(d[O+16]), "+f"(d[O+17]), "+f"(d[O+18]), "+f"(d[O+19]), "+f"(d[O+20]), "+f"(d[O+21]), "+f"(d[O+22]), "+f"(d[O+23]), "+f"(d[O+24]), "+f"(d[O+25]), "+f"(d[O+26]), "+f"(d[O+27]), "+f"(d[O+28]), "+f"(d[O+29]), "+f"(d[O+30]), "+f"(d[O+31])
   : "r"(a0), "r"(a1), "r"(a2), "r"(a3), "l"(db), "n"(TB), "r"(sd));
}
template<int O,int TB,int ACC,int NN> __device__ __forceinline__ void mma_ss128(float (&d)[NN], uint64_t da, uint64_t db, int sd = 0){
  if constexpr (ACC == 1) asm volatile("wgmma.mma_async.sync.aligned.m64n128k16.f32.bf16.bf16 {%0,%1,%2,%3,%4,%5,%6,%7,%8,%9,%10,%11,%12,%13,%14,%15,%16,%17,%18,%19,%20,%21,%22,%23,%24,%25,%26,%27,%28,%29,%30,%31,%32,%33,%34,%35,%36,%37,%38,%39,%40,%41,%42,%43,%44,%45,%46,%47,%48,%49,%50,%51,%52,%53,%54,%55,%56,%57,%58,%59,%60,%61,%62,%63}, %64, %65, 1, 1, 1, %67, %66;"
   : "+f"(d[O+0]), "+f"(d[O+1]), "+f"(d[O+2]), "+f"(d[O+3]), "+f"(d[O+4]), "+f"(d[O+5]), "+f"(d[O+6]), "+f"(d[O+7]), "+f"(d[O+8]), "+f"(d[O+9]), "+f"(d[O+10]), "+f"(d[O+11]), "+f"(d[O+12]), "+f"(d[O+13]), "+f"(d[O+14]), "+f"(d[O+15]), "+f"(d[O+16]), "+f"(d[O+17]), "+f"(d[O+18]), "+f"(d[O+19]), "+f"(d[O+20]), "+f"(d[O+21]), "+f"(d[O+22]), "+f"(d[O+23]), "+f"(d[O+24]), "+f"(d[O+25]), "+f"(d[O+26]), "+f"(d[O+27]), "+f"(d[O+28]), "+f"(d[O+29]), "+f"(d[O+30]), "+f"(d[O+31]), "+f"(d[O+32]), "+f"(d[O+33]), "+f"(d[O+34]), "+f"(d[O+35]), "+f"(d[O+36]), "+f"(d[O+37]), "+f"(d[O+38]), "+f"(d[O+39]), "+f"(d[O+40]), "+f"(d[O+41]), "+f"(d[O+42]), "+f"(d[O+43]), "+f"(d[O+44]), "+f"(d[O+45]), "+f"(d[O+46]), "+f"(d[O+47]), "+f"(d[O+48]), "+f"(d[O+49]), "+f"(d[O+50]), "+f"(d[O+51]), "+f"(d[O+52]), "+f"(d[O+53]), "+f"(d[O+54]), "+f"(d[O+55]), "+f"(d[O+56]), "+f"(d[O+57]), "+f"(d[O+58]), "+f"(d[O+59]), "+f"(d[O+60]), "+f"(d[O+61]), "+f"(d[O+62]), "+f"(d[O+63])
   : "l"(da), "l"(db), "n"(TB & 1), "n"(TB >> 1));
  else if constexpr (ACC == 0) asm volatile("wgmma.mma_async.sync.aligned.m64n128k16.f32.bf16.bf16 {%0,%1,%2,%3,%4,%5,%6,%7,%8,%9,%10,%11,%12,%13,%14,%15,%16,%17,%18,%19,%20,%21,%22,%23,%24,%25,%26,%27,%28,%29,%30,%31,%32,%33,%34,%35,%36,%37,%38,%39,%40,%41,%42,%43,%44,%45,%46,%47,%48,%49,%50,%51,%52,%53,%54,%55,%56,%57,%58,%59,%60,%61,%62,%63}, %64, %65, 0, 1, 1, %67, %66;"
   : "=f"(d[O+0]), "=f"(d[O+1]), "=f"(d[O+2]), "=f"(d[O+3]), "=f"(d[O+4]), "=f"(d[O+5]), "=f"(d[O+6]), "=f"(d[O+7]), "=f"(d[O+8]), "=f"(d[O+9]), "=f"(d[O+10]), "=f"(d[O+11]), "=f"(d[O+12]), "=f"(d[O+13]), "=f"(d[O+14]), "=f"(d[O+15]), "=f"(d[O+16]), "=f"(d[O+17]), "=f"(d[O+18]), "=f"(d[O+19]), "=f"(d[O+20]), "=f"(d[O+21]), "=f"(d[O+22]), "=f"(d[O+23]), "=f"(d[O+24]), "=f"(d[O+25]), "=f"(d[O+26]), "=f"(d[O+27]), "=f"(d[O+28]), "=f"(d[O+29]), "=f"(d[O+30]), "=f"(d[O+31]), "=f"(d[O+32]), "=f"(d[O+33]), "=f"(d[O+34]), "=f"(d[O+35]), "=f"(d[O+36]), "=f"(d[O+37]), "=f"(d[O+38]), "=f"(d[O+39]), "=f"(d[O+40]), "=f"(d[O+41]), "=f"(d[O+42]), "=f"(d[O+43]), "=f"(d[O+44]), "=f"(d[O+45]), "=f"(d[O+46]), "=f"(d[O+47]), "=f"(d[O+48]), "=f"(d[O+49]), "=f"(d[O+50]), "=f"(d[O+51]), "=f"(d[O+52]), "=f"(d[O+53]), "=f"(d[O+54]), "=f"(d[O+55]), "=f"(d[O+56]), "=f"(d[O+57]), "=f"(d[O+58]), "=f"(d[O+59]), "=f"(d[O+60]), "=f"(d[O+61]), "=f"(d[O+62]), "=f"(d[O+63])
   : "l"(da), "l"(db), "n"(TB & 1), "n"(TB >> 1));
  else asm volatile("{\n.reg .pred p;\nsetp.ne.b32 p, %68, 0;\nwgmma.mma_async.sync.aligned.m64n128k16.f32.bf16.bf16 {%0,%1,%2,%3,%4,%5,%6,%7,%8,%9,%10,%11,%12,%13,%14,%15,%16,%17,%18,%19,%20,%21,%22,%23,%24,%25,%26,%27,%28,%29,%30,%31,%32,%33,%34,%35,%36,%37,%38,%39,%40,%41,%42,%43,%44,%45,%46,%47,%48,%49,%50,%51,%52,%53,%54,%55,%56,%57,%58,%59,%60,%61,%62,%63}, %64, %65, p, 1, 1, %67, %66;\n}"
   : "+f"(d[O+0]), "+f"(d[O+1]), "+f"(d[O+2]), "+f"(d[O+3]), "+f"(d[O+4]), "+f"(d[O+5]), "+f"(d[O+6]), "+f"(d[O+7]), "+f"(d[O+8]), "+f"(d[O+9]), "+f"(d[O+10]), "+f"(d[O+11]), "+f"(d[O+12]), "+f"(d[O+13]), "+f"(d[O+14]), "+f"(d[O+15]), "+f"(d[O+16]), "+f"(d[O+17]), "+f"(d[O+18]), "+f"(d[O+19]), "+f"(d[O+20]), "+f"(d[O+21]), "+f"(d[O+22]), "+f"(d[O+23]), "+f"(d[O+24]), "+f"(d[O+25]), "+f"(d[O+26]), "+f"(d[O+27]), "+f"(d[O+28]), "+f"(d[O+29]), "+f"(d[O+30]), "+f"(d[O+31]), "+f"(d[O+32]), "+f"(d[O+33]), "+f"(d[O+34]), "+f"(d[O+35]), "+f"(d[O+36]), "+f"(d[O+37]), "+f"(d[O+38]), "+f"(d[O+39]), "+f"(d[O+40]), "+f"(d[O+41]), "+f"(d[O+42]), "+f"(d[O+43]), "+f"(d[O+44]), "+f"(d[O+45]), "+f"(d[O+46]), "+f"(d[O+47]), "+f"(d[O+48]), "+f"(d[O+49]), "+f"(d[O+50]), "+f"(d[O+51]), "+f"(d[O+52]), "+f"(d[O+53]), "+f"(d[O+54]), "+f"(d[O+55]), "+f"(d[O+56]), "+f"(d[O+57]), "+f"(d[O+58]), "+f"(d[O+59]), "+f"(d[O+60]), "+f"(d[O+61]), "+f"(d[O+62]), "+f"(d[O+63])
   : "l"(da), "l"(db), "n"(TB & 1), "n"(TB >> 1), "r"(sd));
}
template<int O,int TB,int ACC,int NN> __device__ __forceinline__ void mma_rs128(float (&d)[NN], uint32_t a0, uint32_t a1, uint32_t a2, uint32_t a3, uint64_t db, int sd = 0){
  if constexpr (ACC == 1) asm volatile("wgmma.mma_async.sync.aligned.m64n128k16.f32.bf16.bf16 {%0,%1,%2,%3,%4,%5,%6,%7,%8,%9,%10,%11,%12,%13,%14,%15,%16,%17,%18,%19,%20,%21,%22,%23,%24,%25,%26,%27,%28,%29,%30,%31,%32,%33,%34,%35,%36,%37,%38,%39,%40,%41,%42,%43,%44,%45,%46,%47,%48,%49,%50,%51,%52,%53,%54,%55,%56,%57,%58,%59,%60,%61,%62,%63}, {%64,%65,%66,%67}, %68, 1, 1, 1, %69;"
   : "+f"(d[O+0]), "+f"(d[O+1]), "+f"(d[O+2]), "+f"(d[O+3]), "+f"(d[O+4]), "+f"(d[O+5]), "+f"(d[O+6]), "+f"(d[O+7]), "+f"(d[O+8]), "+f"(d[O+9]), "+f"(d[O+10]), "+f"(d[O+11]), "+f"(d[O+12]), "+f"(d[O+13]), "+f"(d[O+14]), "+f"(d[O+15]), "+f"(d[O+16]), "+f"(d[O+17]), "+f"(d[O+18]), "+f"(d[O+19]), "+f"(d[O+20]), "+f"(d[O+21]), "+f"(d[O+22]), "+f"(d[O+23]), "+f"(d[O+24]), "+f"(d[O+25]), "+f"(d[O+26]), "+f"(d[O+27]), "+f"(d[O+28]), "+f"(d[O+29]), "+f"(d[O+30]), "+f"(d[O+31]), "+f"(d[O+32]), "+f"(d[O+33]), "+f"(d[O+34]), "+f"(d[O+35]), "+f"(d[O+36]), "+f"(d[O+37]), "+f"(d[O+38]), "+f"(d[O+39]), "+f"(d[O+40]), "+f"(d[O+41]), "+f"(d[O+42]), "+f"(d[O+43]), "+f"(d[O+44]), "+f"(d[O+45]), "+f"(d[O+46]), "+f"(d[O+47]), "+f"(d[O+48]), "+f"(d[O+49]), "+f"(d[O+50]), "+f"(d[O+51]), "+f"(d[O+52]), "+f"(d[O+53]), "+f"(d[O+54]), "+f"(d[O+55]), "+f"(d[O+56]), "+f"(d[O+57]), "+f"(d[O+58]), "+f"(d[O+59]), "+f"(d[O+60]), "+f"(d[O+61]), "+f"(d[O+62]), "+f"(d[O+63])
   : "r"(a0), "r"(a1), "r"(a2), "r"(a3), "l"(db), "n"(TB));
  else if constexpr (ACC == 0) asm volatile("wgmma.mma_async.sync.aligned.m64n128k16.f32.bf16.bf16 {%0,%1,%2,%3,%4,%5,%6,%7,%8,%9,%10,%11,%12,%13,%14,%15,%16,%17,%18,%19,%20,%21,%22,%23,%24,%25,%26,%27,%28,%29,%30,%31,%32,%33,%34,%35,%36,%37,%38,%39,%40,%41,%42,%43,%44,%45,%46,%47,%48,%49,%50,%51,%52,%53,%54,%55,%56,%57,%58,%59,%60,%61,%62,%63}, {%64,%65,%66,%67}, %68, 0, 1, 1, %69;"
   : "=f"(d[O+0]), "=f"(d[O+1]), "=f"(d[O+2]), "=f"(d[O+3]), "=f"(d[O+4]), "=f"(d[O+5]), "=f"(d[O+6]), "=f"(d[O+7]), "=f"(d[O+8]), "=f"(d[O+9]), "=f"(d[O+10]), "=f"(d[O+11]), "=f"(d[O+12]), "=f"(d[O+13]), "=f"(d[O+14]), "=f"(d[O+15]), "=f"(d[O+16]), "=f"(d[O+17]), "=f"(d[O+18]), "=f"(d[O+19]), "=f"(d[O+20]), "=f"(d[O+21]), "=f"(d[O+22]), "=f"(d[O+23]), "=f"(d[O+24]), "=f"(d[O+25]), "=f"(d[O+26]), "=f"(d[O+27]), "=f"(d[O+28]), "=f"(d[O+29]), "=f"(d[O+30]), "=f"(d[O+31]), "=f"(d[O+32]), "=f"(d[O+33]), "=f"(d[O+34]), "=f"(d[O+35]), "=f"(d[O+36]), "=f"(d[O+37]), "=f"(d[O+38]), "=f"(d[O+39]), "=f"(d[O+40]), "=f"(d[O+41]), "=f"(d[O+42]), "=f"(d[O+43]), "=f"(d[O+44]), "=f"(d[O+45]), "=f"(d[O+46]), "=f"(d[O+47]), "=f"(d[O+48]), "=f"(d[O+49]), "=f"(d[O+50]), "=f"(d[O+51]), "=f"(d[O+52]), "=f"(d[O+53]), "=f"(d[O+54]), "=f"(d[O+55]), "=f"(d[O+56]), "=f"(d[O+57]), "=f"(d[O+58]), "=f"(d[O+59]), "=f"(d[O+60]), "=f"(d[O+61]), "=f"(d[O+62]), "=f"(d[O+63])
   : "r"(a0), "r"(a1), "r"(a2), "r"(a3), "l"(db), "n"(TB));
  else asm volatile("{\n.reg .pred p;\nsetp.ne.b32 p, %70, 0;\nwgmma.mma_async.sync.aligned.m64n128k16.f32.bf16.bf16 {%0,%1,%2,%3,%4,%5,%6,%7,%8,%9,%10,%11,%12,%13,%14,%15,%16,%17,%18,%19,%20,%21,%22,%23,%24,%25,%26,%27,%28,%29,%30,%31,%32,%33,%34,%35,%36,%37,%38,%39,%40,%41,%42,%43,%44,%45,%46,%47,%48,%49,%50,%51,%52,%53,%54,%55,%56,%57,%58,%59,%60,%61,%62,%63}, {%64,%65,%66,%67}, %68, p, 1, 1, %69;\n}"
   : "+f"(d[O+0]), "+f"(d[O+1]), "+f"(d[O+2]), "+f"(d[O+3]), "+f"(d[O+4]), "+f"(d[O+5]), "+f"(d[O+6]), "+f"(d[O+7]), "+f"(d[O+8]), "+f"(d[O+9]), "+f"(d[O+10]), "+f"(d[O+11]), "+f"(d[O+12]), "+f"(d[O+13]), "+f"(d[O+14]), "+f"(d[O+15]), "+f"(d[O+16]), "+f"(d[O+17]), "+f"(d[O+18]), "+f"(d[O+19]), "+f"(d[O+20]), "+f"(d[O+21]), "+f"(d[O+22]), "+f"(d[O+23]), "+f"(d[O+24]), "+f"(d[O+25]), "+f"(d[O+26]), "+f"(d[O+27]), "+f"(d[O+28]), "+f"(d[O+29]), "+f"(d[O+30]), "+f"(d[O+31]), "+f"(d[O+32]), "+f"(d[O+33]), "+f"(d[O+34]), "+f"(d[O+35]), "+f"(d[O+36]), "+f"(d[O+37]), "+f"(d[O+38]), "+f"(d[O+39]), "+f"(d[O+40]), "+f"(d[O+41]), "+f"(d[O+42]), "+f"(d[O+43]), "+f"(d[O+44]), "+f"(d[O+45]), "+f"(d[O+46]), "+f"(d[O+47]), "+f"(d[O+48]), "+f"(d[O+49]), "+f"(d[O+50]), "+f"(d[O+51]), "+f"(d[O+52]), "+f"(d[O+53]), "+f"(d[O+54]), "+f"(d[O+55]), "+f"(d[O+56]), "+f"(d[O+57]), "+f"(d[O+58]), "+f"(d[O+59]), "+f"(d[O+60]), "+f"(d[O+61]), "+f"(d[O+62]), "+f"(d[O+63])
   : "r"(a0), "r"(a1), "r"(a2), "r"(a3), "l"(db), "n"(TB), "r"(sd));
}

#define NEARLY 0
#define XAHEAD 3
#define HEADN 6
#define WBATCH 1
#define WB 8
#define WSLEEP 20
#define XSPREAD 4
#define NOSEND 0
#define MSPLIT 3
#define PFALL 1
#define L2PF 1
#define STAG 0
#define EPF 2
#define XNB 2
#define FNB 0
#define GNB 0
#define SPACE 40
#define WPF 1
#define WAFTER 7
#define WPACE 0
#define GATE_AT 4
#define TPACE 40
#define PFMODE 0
#define MAPMODE 1
template <int V> struct IC { static constexpr int value = V; };
struct Maps { CUtensorMap x, ft, g64, u64, e, wr, wi, xs, ts, t, g32, u32, d224, o; };

constexpr int NCTA = 130;
constexpr int U = 16384;
constexpr int TB = 36864;
constexpr int OFF_RING = 8 * U, OFF_Z = 9 * U, OFF_XB = 12 * U, OFF_T = 13 * U, OFF_D = OFF_T;
constexpr int OFF_BAR = 14 * U, OFF_SP = OFF_BAR + 512, OFF_G = OFF_SP + 1024 + 128;
constexpr int SMEM_BYTES = OFF_G + 512;
constexpr int B_FX = 0, B_FA = 8, B_FT = 12, B_Z = 16, B_W = 24, B_HX = 25, B_TL = 26, B_HP = 27, B_WR = 30, B_E0 = 34;
constexpr int B_EA = 35, B_ET = 39, B_PZ = 43, B_RDY = 45, B_FE = 46;
constexpr int B_T = 50, B_XS = 51, B_G = 53, NBAR = 54;
__host__ __device__ constexpr int rslot(int n) { return n & 3; }
__host__ __device__ constexpr int rpar(int n) { return (n >> 2) & 1; }

__global__ void __cluster_dims__(2, 1, 1) __launch_bounds__(512, 1)
fused_kernel(Work* __restrict__ ws, const uint16_t* __restrict__ dtab, const __nv_bfloat16* __restrict__ w_r, const __nv_bfloat16* __restrict__ w_i,
             const __nv_bfloat16* __restrict__ gate_w, const __nv_bfloat16* __restrict__ x, const uint16_t* __restrict__ ftab,
             const __nv_bfloat16* __restrict__ Wg, const __nv_bfloat16* __restrict__ Wu, const __grid_constant__ Maps maps) {
  extern __shared__ __align__(1024) uint8_t smem[];
  const uint32_t sb = smem_u32(smem);
  const uint32_t bars = sb + OFF_BAR;
  const int tid = threadIdx.x, lane = tid & 31;
  const int warp = __shfl_sync(0xffffffffu, tid >> 5, 0);
  const bool helper = blockIdx.x >= 128;
  const int cl = (blockIdx.x >> 1) & 63, rank = blockIdx.x & 1;
  const int q4 = (cl & 1) | ((cl >> 2) & 2), rb = ((cl >> 1) & 3) | ((cl >> 4) << 2);
  const int j = 2 * q4 + rank;
  const int f_full = 448 * q4 + (rank ? 256 : 0);
  const int f_half = 448 * q4 + (rank ? 224 : 192);
  const int kg = 2 * j + (rb >> 3), tn = rb & 7;

  if (tid == 64) { PROF_EV(0); PROF_CK(40); }
  if (warp < 8) {
    if (!helper) {
      if (tid < 16 * XNB) {
        const int r = 16 * j + (tid & 15);
        asm volatile("prefetch.global.L2 [%0];" ::"l"(x + (size_t)(2 * rb + (r >> 6) + 32 * (r & 63)) * 512 + 64 * (tid >> 4)));
      } else if (tid >= 128 && tid < 128 + 4 * FNB) {
        asm volatile("prefetch.global.L2 [%0];" ::"l"(ftab + (64 * j + 4 * rb + (tid & 3)) * 512 + 64 * ((tid - 128) >> 2)));
      } else if (tid >= 192 && tid < 192 + 8 * GNB) {
        asm volatile("prefetch.global.L2 [%0];" ::"l"(((tid & 4) ? Wu : Wg) + (size_t)(64 * ((tid - 192) >> 3) + 4 * rb + (tid & 3)) * 1792 + f_full));
      }
    }
    asm volatile("barrier.cluster.arrive.relaxed.aligned;" ::: "memory");
    asm volatile("setmaxnreg.inc.sync.aligned.u32 192;");
    if (!helper) {
      const int wg = warp >> 2, w = warp & 3, g = lane >> 2;
      const bool elect = (tid & 127) == 0;
      float cX[32], cA[64], cB[64], cC[64], ci[64], ct[64];
      const int zero = blockIdx.x >> 16;
      uint32_t h[56], yf[16];
      const uint32_t d0 = (sb & 0x3FFFF) >> 4;
      const uint32_t dK = d0 | (1u << 16), dN = d0 | (512u << 16);
      const uint32_t dX = dK + wg * 512;
      constexpr uint32_t RING = OFF_RING >> 4;
      auto waitA = [&](int n) { mbar_wait(bars + 8 * (B_FA + rslot(n)), rpar(n)); };
      auto freeA = [&](int n) { mbar_arrive_if(elect, bars + 8 * (B_EA + rslot(n))); };
      auto nop = [] {};

      asm volatile("bar.sync 0, 384;" ::: "memory");
#pragma unroll 1
      for (int i = 0; i < 4; i++) {
        const uint64_t dx = d128(dX + i * 2048), df = d128(dK + (OFF_XB >> 4) + (i & 1) * 1024);
        mbar_wait(bars + 8 * (B_FX + 2 * i), 0);
        wg_fence();
        mma_ss64<0, 0, 2>(cX, df, dx, i);
        mma_ss64<0, 0, 1>(cX, df + 2, dx + 2);
        wg_commit(); wg_wait<1>();
        mbar_arrive_if(elect && i, bars + 8 * (B_EA + rslot(i - 1)));
        mma_ss64<0, 0, 1>(cX, df + 4, dx + 4);
        mma_ss64<0, 0, 1>(cX, df + 6, dx + 6);
        if (i == 0 && tid == 0) PROF_EV(1);
        mbar_wait(bars + 8 * (B_FX + 2 * i + 1), 0);
        wg_fence();
#pragma unroll
        for (int k = 0; k < 4; k++) mma_ss64<0, 0, 1>(cX, df + (512 + k * 2), dx + (1024 + k * 2));
        wg_commit();
        waitA(i);
        wg_fence();
        const uint64_t da = d128(dX + i * 1024), db = d128(dN + RING + i * 1024);
        mma_ss128<0, 1, 2>(cA, da, db, i);
        wg_commit(); wg_wait<1>();
        mbar_arrive_if(elect, bars + 8 * (B_FE + i));
#pragma unroll
        for (int k = 1; k < 4; k++) mma_ss128<0, 1, 1>(cA, da + k * 2, db + k * 128);
        wg_commit();
      }
      fence_regs<0, 32>(cX);
#pragma unroll
      for (int e = 0; e < 16; e++) yf[e] = pack_pin(cX[2 * e], cX[2 * e + 1]);
      if (tid == 0) { PROF_EV(2); PROF_CK(42); }
      {
        waitA(4); mbar_wait(bars + 8 * B_E0, 0);
        const uint64_t de = d128(dN + (wg ? RING : OFF_XB >> 4));
        wg_fence();
        mma_rs128<0, 1, 0>(cB, yf[0], yf[1], yf[2], yf[3], de);
        wg_commit();
        wg_wait<1>();
        freeA(3);
#pragma unroll
        for (int k = 1; k < 4; k++) mma_rs128<0, 1, 1>(cB, yf[4 * k], yf[4 * k + 1], yf[4 * k + 2], yf[4 * k + 3], de + k * 128);
        wg_commit();
      }
      bool rel = false;
      auto acquire = [&](int n) {
        rel = elect;
        if (!mbar_try(bars + 8 * (B_FA + rslot(n)), rpar(n))) { wg_wait<0>(); freeA(n - 1); rel = false; waitA(n); }
      };
      auto freeP = [&](int n) { mbar_arrive_if(rel, bars + 8 * (B_EA + rslot(n - 1))); };
      auto ffn_step = [&](auto first, auto split, float (&acc)[64], int n, int kb, auto done, auto work) {
        constexpr int SPLIT = decltype(split)::value;
        acquire(n);
        wg_fence();
        const uint64_t dx = d128(dX + kb * 1024), db = d128(dN + RING + rslot(n) * 1024);
        mma_ss128<0, 1, decltype(first)::value>(acc, dx, db, kb);
#pragma unroll
        for (int k = 1; k < SPLIT; k++) mma_ss128<0, 1, 1>(acc, dx + k * 2, db + k * 128);
        wg_commit();
        work();
        wg_wait<1>();
        freeP(n);
        done();
        if (SPLIT < 4) {
          wg_fence();
#pragma unroll
          for (int k = SPLIT; k < 4; k++) mma_ss128<0, 1, 1>(acc, dx + k * 2, db + k * 128);
          wg_commit();
        }
      };
      {
        const int s0 = 2 * rb + wg, kr = 2 * ((s0 & 1) | ((s0 & 4) >> 1));
        const int m = lane >> 3, r = lane & 7;
        const uint32_t a0 = sb + OFF_XB + wg * 8192 + (((w >> 1) * 8 + (m >> 1)) * 2 + (w & 1)) * 256 + (m & 1) * 128 + ((r ^ (kr + (m & 1))) << 4);
        ffn_step(IC<1>(), IC<4>(), cA, 5, 4, [&] { fence_regs<0, 64>(cB); }, nop);
        asm volatile("bar.sync 5, 256;" ::: "memory");
        auto stage = [&](int i) {
          stsm4t(a0 + i * 1024, pack_bf16(cB[8 * i] - cB[34 + 8 * i], cB[8 * i + 1] - cB[35 + 8 * i]),
                 pack_bf16(cB[32 + 8 * i] + cB[8 * i + 2], cB[33 + 8 * i] + cB[8 * i + 3]),
                 pack_bf16(cB[8 * i + 4] - cB[38 + 8 * i], cB[8 * i + 5] - cB[39 + 8 * i]),
                 pack_bf16(cB[36 + 8 * i] + cB[8 * i + 6], cB[37 + 8 * i] + cB[8 * i + 7]));
          if (j == 0 && w == 0) {
            const uint32_t a1 = r ? sb + OFF_SP + 1024 : sb + OFF_SP + wg * 512 + (m & 1) * 256 + (m >> 1) * 128;
#pragma unroll
            for (int n = 2 * i; n < 2 * i + 2; n++)
              asm volatile("stmatrix.sync.aligned.m8n8.x4.shared.b16 [%0], {%1,%2,%3,%4};" ::"r"(a1 + ((n ^ (kr + (m >> 1)) ^ r) << 4)),
                           "r"(pack_bf16(cB[4 * n], cB[4 * n + 1])), "r"(pack_bf16(cB[4 * n + 2], cB[4 * n + 3])),
                           "r"(pack_bf16(cB[32 + 4 * n], cB[33 + 4 * n])), "r"(pack_bf16(cB[34 + 4 * n], cB[35 + 4 * n])) : "memory");
          }
        };
        auto publish = [&] {
          asm volatile("fence.proxy.async.shared::cta;" ::: "memory");
          __syncwarp();
          mbar_arrive_if(lane == 0, bars + 8 * (B_XS + wg));
          if (tid == 0) PROF_EV(3);
        };
        stage(0);
        ffn_step(IC<1>(), IC<1>(), cA, 6, 5, nop, nop);
        stage(1);
        ffn_step(IC<1>(), IC<1>(), cA, 7, 6, nop, nop);
        stage(2);
        ffn_step(IC<1>(), IC<2>(), cA, 8, 7, [&] { stage(3); }, nop);
        publish();
      }
      float g0 = 0.f, g1 = 0.f;
      uint32_t tag = 0;
      auto glu = [&](auto& acc, int half, int ho, int i0, int i1) {
#pragma unroll
        for (int i = i0; i < i1; i++) {
          const float o = 1.0f - ((i & 1) ? g1 : g0);
          asm volatile("" : "+f"(acc[2 * i]), "+f"(acc[2 * i + 1]), "+f"(acc[half + 2 * i]), "+f"(acc[half + 1 + 2 * i])::"memory");
          h[ho + i] = pack_pin(fmaxf(acc[2 * i], 0.f) * acc[half + 2 * i] * o, fmaxf(acc[2 * i + 1], 0.f) * acc[half + 1 + 2 * i] * o);
        }
      };
      ffn_step(IC<2>(), IC<1>(), cB, 9, zero, nop, nop);
#pragma unroll 1
      for (int kb = 1; kb < 8; kb++)
        ffn_step(IC<1>(), IC<1>(), cB, 9 + kb, kb, nop, [&] {
          if (kb == 4 + wg) {
            mbar_wait(bars + 8 * B_G, 0);
            const uint32_t gb0 = *(const uint32_t*)(smem + OFF_G + (wg * 64 + w * 16 + g) * 4), gb1 = *(const uint32_t*)(smem + OFF_G + (wg * 64 + w * 16 + g + 8) * 4);
            tag = gb0 & 1; g0 = __uint_as_float(gb0 & ~1u); g1 = __uint_as_float(gb1 & ~1u);
            glu(cA, 32, 0, 0, 8);
          } else if (kb == 6 + wg) glu(cA, 32, 0, 8, 16);
        });
      if (tid == 0) { PROF_EV(4); PROF_CK(43); }
      ffn_step(IC<0>(), IC<1>(), cC, 17, 0, nop, nop);
#pragma unroll 1
      for (int kb = 1; kb < 8; kb++)
        ffn_step(IC<1>(), IC<1>(), cC, 17 + kb, kb, nop, [&] {
          if (kb == 1 + wg) glu(cB, 32, 16, 0, 8);
          else if (kb == 3 + wg) glu(cB, 32, 16, 8, 16);
        });
      if (tid == 0) { PROF_EV(5); PROF_CK(44); }
      auto m_step = [&](auto first, int i) {
        acquire(25 + i);
        wg_fence();
        const uint64_t dx = d128(dX + i * 2048), dm = d64(dN + RING + rslot(25 + i) * 1024);
        mma_ss64<0, 1, decltype(first)::value>(ct, dx, dm);
#pragma unroll
        for (int k = 1; k < MSPLIT; k++) mma_ss64<0, 1, 1>(ct, dx + ((k >> 2) * 1024 + (k & 3) * 2), dm + k * 64);
        wg_commit();
        wg_wait<1>();
        mbar_arrive_if(rel && i < 3, bars + 8 * (B_EA + rslot(24 + i)));
        mbar_arrive_if(elect && i, bars + 8 * (B_ET + i - 1));
        wg_fence();
#pragma unroll
        for (int k = MSPLIT; k < 8; k++) mma_ss64<0, 1, 1>(ct, dx + ((k >> 2) * 1024 + (k & 3) * 2), dm + k * 64);
        wg_commit();
      };
      auto freeT = [&](int t) { mbar_arrive_if(elect, bars + 8 * (B_ET + t)); };
      m_step(IC<0>(), 0);
#pragma unroll 1
      for (int i = 1; i < 5; i++) {
        if (i == 1 + wg) glu(cC, 32, 32, 0, 8);
        else if (i == 3 + wg) glu(cC, 32, 32, 8, 16);
        if (i < 4) m_step(IC<1>(), i);
      }
      waitA(29 + wg);
      if (tid == 0) PROF_EV(6);
      if (tid == 128) PROF_EV(27);
      mbar_wait(bars + 8 * (j == 0 ? B_T : B_TL), 0);
      if (tid == 0) { PROF_EV(7); PROF_CK(45); }
      wg_fence();
      {
        const uint64_t dt = d128(dN + (OFF_T >> 4) + wg * 512), de = d128(dK + RING + (1 + wg) * 1024);
        mma_ss64<0, 1, 0>(ci, de, dt);
        mma_ss64<32, 1, 0>(ci, de + 512, dt);
#pragma unroll
        for (int k = 1; k < 4; k++) {
          mma_ss64<0, 1, 1>(ci, de + k * 2, dt + k * 128);
          mma_ss64<32, 1, 1>(ci, de + (512 + k * 2), dt + k * 128);
        }
        wg_commit();
        wg_wait<1>();
        freeT(3);
        fence_regs<0, 32>(ct);
        glu(ct, 16, 48, 0, 8);
      }

      auto twait = [&](uint32_t bar, uint32_t par, int) { mbar_wait(bar, par); };
      const int fo = warp * 128 + lane;
      auto fetch = [&](uint4 (&pv)[4], int z) {
        twait(bars + 8 * (z < 4 ? B_Z + 2 * z + wg : B_HP + z - 4), 0, 8 + z);
        const uint8_t* src = smem + (z < 5 ? OFF_Z + z * U : (z - 5) * U) + fo * 16;
#pragma unroll
        for (int i = 0; i < 4; i++) pv[i] = *(const uint4*)(src + i * 512);
      };
      auto check = [&](uint4 (&pv)[4], int z) {
        const uint32_t t0 = (uint32_t)clock();
        while (__any_sync(0xffffffffu, ((pv[0].x ^ tag) | (pv[1].x ^ tag) | (pv[2].x ^ tag) | (pv[3].x ^ tag)) & 1)) {
#pragma unroll
          for (int i = 0; i < 4; i++) pv[i] = ld_x4(ws->part + (size_t)((rb * 8 + j) * 3 + z - 4) * 1024 + fo + i * 32);
          spin_guard(t0);
        }
#pragma unroll
        for (int i = 0; i < 4; i++) pv[i].x &= ~1u;
      };
      auto head = [&](auto off, int t, bool init) {
        constexpr int O = decltype(off)::value;
        twait(bars + 8 * (B_FT + (t & 3)), t >> 2, t);
        const uint64_t db = d128(dN + (t & 3) * (TB >> 4) + rank * 256);
        wg_fence();
        mma_rs64<O, 1, 2>(ct, h[0], h[1], h[2], h[3], db, zero + init);
#pragma unroll
        for (int k = 1; k < 6; k++) mma_rs64<O, 1, 1>(ct, h[4 * k], h[4 * k + 1], h[4 * k + 2], h[4 * k + 3], db + k * 128);
        wg_commit();
        wg_wait<1>();
      };
      auto rest = [&](auto off, int t, int z) {
        constexpr int O = decltype(off)::value, P = 32 - O;
        const uint64_t db = d128(dN + (t & 3) * (TB >> 4)), dw = db + rank * 256, dm = db + (rank ? 0 : 1536);
        wg_fence();
#pragma unroll
        for (int k = 6; k < 12; k++) mma_rs64<O, 1, 1>(ct, h[4 * k], h[4 * k + 1], h[4 * k + 2], h[4 * k + 3], dw + k * 128);
        wg_commit();
        uint4 pv[4];
        if (z >= 0) fetch(pv, z);
        wg_fence();
#pragma unroll
        for (int k = 0; k < 2; k++) mma_rs64<O, 1, 1>(ct, h[48 + 4 * k], h[49 + 4 * k], h[50 + 4 * k], h[51 + 4 * k], dm + k * 128);
#pragma unroll
        for (int k = 0; k < 4; k++) mma_rs64<O, 1, 1>(ct, yf[4 * k], yf[4 * k + 1], yf[4 * k + 2], yf[4 * k + 3], db + (14 + k) * 128);
        wg_commit();
        if (z >= 0) {
          if (z >= 4) check(pv, z);
#pragma unroll
          for (int i = 0; i < 4; i++) {
            const uint32_t a[4] = {pv[i].x, pv[i].y, pv[i].z, pv[i].w};
#pragma unroll
            for (int e = 0; e < 4; e++) { ct[P + 8 * i + 2 * e] = bf_lo(a[e]); ct[P + 8 * i + 2 * e + 1] = bf_hi(a[e]); }
          }
        }
      };
      const uint32_t peerZ = mapa(sb + OFF_Z + fo * 16, rank ^ 1), peerB = mapa(bars + 8 * (B_Z + wg), rank ^ 1);
      auto send = [&](auto off, int t) {
        constexpr int O = decltype(off)::value;
        fence_regs<O, 32>(ct);
        const bool grid = t >= 3 && t < 6;
        const int z = grid ? t - 3 : t == 6 ? 3 : t;
        uint32_t pk[16];
#pragma unroll
        for (int i = 0; i < 16; i++) pk[i] = pack_bf16(ct[O + 2 * i], ct[O + 2 * i + 1]);
        if (grid) {
          const int owner = rb * 8 + 2 * ((q4 + z + 1) & 3) + rank;
          uint4* dst = ws->part + (size_t)(owner * 3 + z) * 1024 + fo;
#pragma unroll
          for (int i = 0; i < 4; i++) st_x4(dst + i * 32, (pk[4 * i] & ~1u) | tag, pk[4 * i + 1], pk[4 * i + 2], pk[4 * i + 3]);
          __syncwarp();
          hint_add_if(lane == 0, &ws->cntP[32 * owner + z]);
        } else {
#pragma unroll
          for (int i = 0; i < 4; i++)
            asm volatile("st.async.weak.shared::cluster.mbarrier::complete_tx::bytes.v4.b32 [%0], {%1,%2,%3,%4}, [%5];" ::"r"(peerZ + z * U + i * 512),
                         "r"(pk[4 * i]), "r"(pk[4 * i + 1]), "r"(pk[4 * i + 2]), "r"(pk[4 * i + 3]), "r"(peerB + 16 * z) : "memory");
        }
      };
      asm volatile("barrier.cluster.wait.aligned;" ::: "memory");
      head(IC<0>(), 0, false);
      if (elect) asm volatile("mbarrier.arrive.shared::cluster.b64 _, [%0];" ::"r"(mapa(bars + 8 * B_RDY, rank ^ 1)) : "memory");
      mbar_arrive_if(elect, bars + 8 * (B_PZ + 1));
      fence_regs<0, 64>(ci);
#pragma unroll
      for (int i = 0; i < 16; i++) {
        const float gg = ((i & 1) ? g1 : g0) * (2.0f / (2048.0f * 512.0f));
        if (i & 2) yf[i] = pack_pin((ci[2 * i] - ci[28 + 2 * i]) * gg, (ci[2 * i + 1] - ci[29 + 2 * i]) * gg);
        else yf[i] = pack_pin((ci[2 * i] + ci[36 + 2 * i]) * gg, (ci[2 * i + 1] + ci[37 + 2 * i]) * gg);
      }
      if (tid == 0) PROF_EV(8);
      if (tid == 128) PROF_EV(28);
#pragma unroll 1
      for (int t = 0;; t += 2) {
        rest(IC<0>(), t, t - 2);
        head(IC<32>(), t + 1, t >= 2);
        mbar_arrive_if(elect && t < 6, bars + 8 * (B_ET + t));
        if (t == 0) twait(bars + 8 * B_RDY, 0, 15);
        send(IC<0>(), t);
        rest(IC<32>(), t + 1, (t & 2) ? t - 1 : -1);
        if (t == 6) break;
        head(IC<0>(), t + 2, t == 2);
        mbar_arrive_if(elect && t < 4, bars + 8 * (B_ET + t + 1));
        send(IC<32>(), t + 1);
      }
      if (tid == 0) { PROF_EV(9); PROF_CK(46); }
      if (tid == 128) PROF_EV(29);
      {
        float (&sum)[64] = ct;
        uint4 p2[4], p3[4];
        fetch(p3, 3);
        if (tid == 0) PROF_EV(25);
        fetch(p2, 6);
        if (tid == 0) PROF_EV(24);
        check(p2, 6);
#pragma unroll
        for (int i = 0; i < 4; i++) {
          const uint32_t b[4] = {p2[i].x, p2[i].y, p2[i].z, p2[i].w}, c[4] = {p3[i].x, p3[i].y, p3[i].z, p3[i].w};
#pragma unroll
          for (int e = 0; e < 4; e++) {
            sum[8 * i + 2 * e] += bf_lo(c[e]) + bf_lo(b[e]);
            sum[8 * i + 2 * e + 1] += bf_hi(c[e]) + bf_hi(b[e]);
          }
        }
        if (tid == 0) PROF_EV(14);
        wg_wait<0>();
        fence_regs<32, 32>(ct);
#pragma unroll
        for (int i = 0; i < 32; i++) sum[i] += ct[32 + i];
        const uint32_t stg = sb + OFF_T + warp * 2048;
        const int mr = (lane & 7) + ((lane >> 3) & 1) * 8, mc = lane >> 4;
#pragma unroll
        for (int i = 0; i < 4; i++) {
          const uint32_t a = stg + mr * 128 + (((2 * i + mc) ^ (mr & 7)) << 4);
          asm volatile("stmatrix.sync.aligned.m8n8.x4.shared.b16 [%0], {%1,%2,%3,%4};" ::"r"(a), "r"(pack_bf16(sum[8 * i], sum[8 * i + 1])),
                       "r"(pack_bf16(sum[8 * i + 2], sum[8 * i + 3])), "r"(pack_bf16(sum[8 * i + 4], sum[8 * i + 5])),
                       "r"(pack_bf16(sum[8 * i + 6], sum[8 * i + 7])) : "memory");
        }
        asm volatile("fence.proxy.async.shared::cta;" ::: "memory");
        __syncwarp();
        if (elect_one()) {
          asm volatile("cp.async.bulk.tensor.3d.global.shared::cta.bulk_group [%0, {%2, %3, %4}], [%1];" ::"l"(&maps.o), "r"(stg), "r"(64 * j),
                       "r"(16 * w), "r"(2 * rb + wg) : "memory");
          asm volatile("cp.async.bulk.commit_group;\ncp.async.bulk.wait_group.read 0;" ::: "memory");
        }
      }
      if (tid == 0) { PROF_EV(15); PROF_CK(41); }
      if (tid == 128) PROF_EV(30);
    }
  } else if (warp < 12) {
    asm volatile("setmaxnreg.dec.sync.aligned.u32 104;");
    asm volatile("barrier.cluster.arrive.relaxed.aligned;" ::: "memory");
    const int t = tid - 256, w = warp - 8;
    const uint32_t ep = ld_x1(&ws->epoch[blockIdx.x * 8]);
    const uint32_t tag = (ep + 1) & 1;
    auto w_issue = [&](const CUtensorMap* m) {
          if (elect_one()) { mbar_expect_tx(bars + 8 * (B_WR + w), 3072); tma4d(sb + OFF_T + w * 3072, m, bars + 8 * (B_WR + w), 16 * kg, 0, 2 * w, tn); }
          __syncwarp();
    };
    auto gate_rows = [&] {
      const int r = 16 * j + 4 * w + (lane >> 3);
      const uint4* pg = (const uint4*)gate_w + (lane & 7);
      {
        float a = 0.f;
        asm volatile("bar.sync 4, 256;" ::: "memory");
#pragma unroll 1
        for (int hf = 0; hf < 2; hf++) {
          uint4 v[4], u[4];
#pragma unroll
          for (int kb = 0; kb < 4; kb++) v[kb] = __ldg(pg + (4 * hf + kb) * 8);
          mbar_wait(bars + 8 * (B_FE + 1 + 2 * hf), 0);
          if (hf) w_issue(&maps.wr);
#pragma unroll
          for (int kb = 0; kb < 4; kb++) u[kb] = *(const uint4*)(smem + (4 * hf + kb) * U + r * 128 + (((lane ^ r) & 7) << 4));
#pragma unroll
          for (int kb = 0; kb < 4; kb++) {
            a = fmaf(bf_lo(u[kb].x), bf_lo(v[kb].x), a); a = fmaf(bf_hi(u[kb].x), bf_hi(v[kb].x), a);
            a = fmaf(bf_lo(u[kb].y), bf_lo(v[kb].y), a); a = fmaf(bf_hi(u[kb].y), bf_hi(v[kb].y), a);
            a = fmaf(bf_lo(u[kb].z), bf_lo(v[kb].z), a); a = fmaf(bf_hi(u[kb].z), bf_hi(v[kb].z), a);
            a = fmaf(bf_lo(u[kb].w), bf_lo(v[kb].w), a); a = fmaf(bf_hi(u[kb].w), bf_hi(v[kb].w), a);
          }
        }
#pragma unroll
        for (int o = 4; o; o >>= 1) a += __shfl_xor_sync(0xffffffffu, a, o);
        if ((lane & 7) == 0)
          asm volatile("st.relaxed.gpu.global.f32 [%0], %1;" ::"l"(ws->gate + rb * 128 + r), "f"(tagf(__fdividef(1.0f, 1.0f + __expf(-a)), tag)) : "memory");
        if (t == 0) PROF_EV(18);
      }
    };
    {
      const int g = lane >> 2, q = lane & 3;
      uint32_t wf[32];
      if (!helper) {
        gate_rows();
        const uint32_t wa = sb + OFF_T + w * (3072 + 4) + q * 48 + g * 2;
#pragma unroll 1
        for (int ri = 0; ri < 2; ri++) {
          mbar_wait(bars + 8 * (B_WR + w), ri);
#pragma unroll
          for (int n2 = 0; n2 < 32 / WB; n2++) {
            uint32_t v[WB];
#pragma unroll
            for (int i = 0; i < WB; i++) {
              const int e = n2 * WB + i;
              asm volatile("ld.shared.u16 %0, [%1];" : "=r"(v[i]) : "r"(wa + ((e >> 1) & 7) * 192 + (e & 1) * (1536 + 2) + (e >> 4) * 16) : "memory");
            }
#pragma unroll
            for (int i = 0; i < WB; i++) wf[n2 * WB + i] = __byte_perm(wf[n2 * WB + i], v[i], 0x5432);
            if (WSLEEP) { asm volatile("nanosleep.u32 %0;" ::"r"(WSLEEP + (v[WB - 1] >> 16)) : "memory"); }
          }
          __syncwarp();
          if (ri == 0) w_issue(&maps.wi);
        }
        asm volatile("bar.sync 1, 128;" ::: "memory");
        if (t == 0) PROF_EV(11);
      } else {
        asm volatile("bar.sync 4, 256;" ::: "memory");
        hint_wait(&ws->cntW[0], (ep + 1) * 128u);
        const uint32_t t0 = (uint32_t)clock();
#pragma unroll 1
        for (;;) {
          uint32_t bad = 0;
#pragma unroll
          for (int i = 0; i < 32; i++) {
            const float2 v = ld_x2((const float2*)ws->Wh + (i >> 4) * 2048 + 16 * w + g + 8 * (i & 1) + 64 * q + ((i >> 1) & 7) * 256);
            wf[i] = __float_as_uint(v.x); bad |= __float_as_uint(v.y) ^ tag;
          }
          if (!__any_sync(0xffffffffu, bad & 1)) break;
          spin_guard(t0);
        }
        if (t == 0) PROF_EV(11);
      }
      if (w == 0 && elect_one()) { mbar_expect_tx(bars + 8 * B_W, 8192); bulk_load(sb + OFF_D, dtab, 8192, bars + 8 * B_W); }
      mbar_wait(bars + 8 * B_W, 0);
      mbar_wait(bars + 8 * B_HX, 0);
      if (t == 0) PROF_EV(12);
      const uint32_t dd = (sb & 0x3FFFF) >> 4;
      const uint64_t dF = d128((dd + (OFF_D >> 4)) | (512u << 16)), dI = d128((dd + (OFF_D >> 4)) | (1u << 16)), dA = d128((dd + (OFF_XB >> 4)) | (512u << 16));
      float az[32];
      const int zero = blockIdx.x >> 16;
      uint32_t pf[32];
#pragma unroll
      for (int mt = 0; mt < 2; mt++) {
        wg_fence();
        if (mt == 0) mma_ss64<0, 3, 0>(az, dA, dF);
        else mma_ss64<0, 3, 2>(az, dA + 512, dF, zero);
#pragma unroll
        for (int k = 1; k < 4; k++) mma_ss64<0, 3, 1>(az, dA + (mt * 512 + k * 128), dF + k * 128);
        wg_commit();
        wg_wait<0>();
        fence_regs<0, 32>(az);
#pragma unroll
        for (int i = 0; i < 16; i++) {
          const float wr = bf_lo(wf[16 * mt + i]), wi = bf_hi(wf[16 * mt + i]);
          pf[16 * mt + i] = pack_pin(fmaf(az[2 * i], wr, -az[2 * i + 1] * wi), fmaf(az[2 * i], wi, az[2 * i + 1] * wr));
        }
      }
      if (t == 0) PROF_EV(16);
#pragma unroll
      for (int mt = 0; mt < 2; mt++) {
        wg_fence();
        mma_rs64<0, 0, 2>(az, pf[16 * mt], pf[16 * mt + 1], pf[16 * mt + 2], pf[16 * mt + 3], dI, mt ? (int)helper : zero);
#pragma unroll
        for (int k = 1; k < 4; k++) mma_rs64<0, 0, 1>(az, pf[16 * mt + 4 * k], pf[16 * mt + 4 * k + 1], pf[16 * mt + 4 * k + 2], pf[16 * mt + 4 * k + 3], dI + k * 2);
        wg_commit();
        wg_wait<0>();
        fence_regs<0, 32>(az);
        if (!helper) {
          const int m = lane >> 3, r = lane & 7;
          const int sl = 2 * (m >> 1) + ((r >> 1) & 1) + 4 * (r >> 2);
          const uint32_t a0 = sb + OFF_XB + (2 * w + (m & 1)) * 2048 + sl * 64 + (((mt * 2 + (r & 1)) ^ (sl >> 1)) << 4);
#pragma unroll
          for (int i = 0; i < 4; i++)
            stsm4t(a0 + i * 512, pack_bf16(az[8 * i], az[8 * i + 1]), pack_bf16(az[8 * i + 2], az[8 * i + 3]), pack_bf16(az[8 * i + 4], az[8 * i + 5]),
                   pack_bf16(az[8 * i + 6], az[8 * i + 7]));
        }
      }
      if (helper) {
#pragma unroll
        for (int i = 0; i < 16; i++) {
          const int n = i >> 1, s0 = 8 * (n >> 1) + 2 * (n & 1) + (q & 1) + 4 * (q >> 1);
          if ((n & 1) == (int)(blockIdx.x & 1)) st_u2(ws->Ts + s0 * 64 + 16 * w + g + 8 * (i & 1), pack_bf16(az[2 * i], az[2 * i + 1]), tag);
        }
        __syncwarp();
        hint_add_if(lane == 0, &ws->cntH[0]);
        if (t == 0) { ws->epoch[blockIdx.x * 8] = ep + 1; PROF_EV(13); }
      } else {
        asm volatile("fence.proxy.async.shared::cta;" ::: "memory");
        __syncwarp();
        if (elect_one()) {
          if (t == 0) PROF_EV(17);
          if (SPACE) __nanosleep(SPACE * w);
          asm volatile("cp.async.bulk.tensor.3d.global.shared::cta.bulk_group [%0, {%2, %3, %4}], [%1];" ::"l"(&maps.ts), "r"(sb + OFF_XB + w * 4096),
                       "r"(32 * kg), "r"(0), "r"(8 * tn + 2 * w) : "memory");
          bulk_done_signal(&ws->cntT[32 * j]);
          if (t == 96) PROF_EV(13);
        }
        __syncwarp();
        if (j == 0) {
          hint_wait(&ws->cntH[0], (ep + 1) * 8u);
          const uint32_t t0 = (uint32_t)clock();
          float2 v;
          do { v = ld_x2((const float2*)ws->Ts + 2 * rb * 64 + t); spin_guard(t0); } while (__any_sync(0xffffffffu, (__float_as_uint(v.y) ^ tag) & 1));
          mbar_wait(bars + 8 * B_TL, 0);
          const uint32_t u = __float_as_uint(v.x);
          *(uint16_t*)(smem + OFF_T + t * 128 + ((t & 7) << 4)) = (uint16_t)u;
          *(uint16_t*)(smem + OFF_T + t * 128 + (((t & 7) ^ 1) << 4)) = (uint16_t)(u >> 16);
          asm volatile("fence.proxy.async.shared::cta;" ::: "memory");
          __syncwarp();
          mbar_arrive_if(lane == 0, bars + 8 * B_T);
        }
      }
    }
  } else {
    asm volatile("setmaxnreg.dec.sync.aligned.u32 24;");
    auto xf_load = [&](int q) {
      const uint32_t fb = bars + 8 * (B_FX + q);
      mbar_expect_tx(fb, U + 8192);
      tma3d(sb + q * U, &maps.x, fb, 64 * q, 0, 2 * rb);
      if (q >= 4) mbar_wait(bars + 8 * (B_FE + ((q - 4) >> 1)), 0);
      tma2d(sb + OFF_XB + (q & 3) * 8192, &maps.ft, fb, 64 * q, 64 * j);
    };
    if (elect_one()) {
      if (warp == 14) {
#pragma unroll
        for (int i = 0; i < B_FT; i++) mbar_init(bars + 8 * i, 1);
        asm volatile("fence.mbarrier_init.release.cluster;" ::: "memory");
        if (!helper) {
#pragma unroll 1
          for (int n = 0; n < 2; n++) {
            const uint32_t fb = bars + 8 * (B_FA + n);
            xf_load(2 * n); xf_load(2 * n + 1);
            mbar_expect_tx(fb, U);
            tma2d(sb + OFF_RING + n * U, &maps.g64, fb, f_full, 64 * n);
            tma2d(sb + OFF_RING + n * U + 8192, &maps.u64, fb, f_full, 64 * n);
          }
        }
      } else if (warp == 15) {
#pragma unroll
        for (int i = B_FT; i < NBAR; i++) mbar_init(bars + 8 * i, i < B_EA ? 1 : i < B_T ? 2 : 4);
#pragma unroll
        for (int i = 0; i < 8; i++) mbar_expect_tx(bars + 8 * (B_Z + i), U / 2);
        asm volatile("fence.mbarrier_init.release.cluster;" ::: "memory");
        asm volatile("fence.proxy.async.shared::cta;" ::: "memory");
      } else if (warp == 13) {
#pragma unroll
        for (int i = 1; i < 4; i++) asm volatile("prefetch.tensormap [%0];" ::"l"((const char*)&maps + i * 128) : "memory");
      }
    }
    __syncwarp();
    asm volatile("bar.arrive 0, 384;" ::: "memory");
    asm volatile("bar.arrive 4, 256;" ::: "memory");
    __syncwarp();
    asm volatile("barrier.cluster.arrive.relaxed.aligned;" ::: "memory");
    asm volatile("bar.sync 3, 128;" ::: "memory");
    if (warp == 15 && !helper) {
        mbar_wait(bars + 8 * B_FE, 0);
        const uint32_t tag = (ld_x1(&ws->epoch[blockIdx.x * 8]) + 1) & 1;
        const int c = lane >> 4, jj = 16 * blockIdx.x + (lane & 15), jm = (2048 - jj) & 2047;
        const unsigned short* pr = (const unsigned short*)w_r + 256 * c;
        const unsigned short* pi = (const unsigned short*)w_i + 256 * c;
        const float wr = 0.25f * (bf_lo(__ldg(pr + jj * 257)) + bf_lo(__ldg(pr + jm * 257)));
        const float wi = 0.25f * (bf_lo(__ldg(pi + jj * 257)) - bf_lo(__ldg(pi + jm * 257)));
        st_u2(ws->Wh + c * 2048 + jj, c ? pack_bf16(-wi, wr) : pack_bf16(wr, wi), tag);
        __syncwarp();
        hint_add_if(lane == 0, &ws->cntW[0]);
        mbar_wait(bars + 8 * B_XS, 0);
        const uint32_t t0 = (uint32_t)clock();
        uint4 v;
        do { v = ld_x4(ws->gate + rb * 128 + 4 * lane); spin_guard(t0); } while (__any_sync(0xffffffffu, ((v.x ^ tag) | (v.y ^ tag) | (v.z ^ tag) | (v.w ^ tag)) & 1));
        *(uint4*)(smem + OFF_G + lane * 16) = v;
        __syncwarp();
        mbar_arrive_if(lane < 4, bars + 8 * B_G);
      }
    if ((!helper || warp == 15) && elect_one()) {
      if (warp < 14) {
        const int p = warp - 12;
#pragma unroll 1
        for (int i = 4 + p; i < 14; i += 2) asm volatile("prefetch.tensormap [%0];" ::"l"((const char*)&maps + i * 128) : "memory");
#pragma unroll 1
        for (int n = 2; n < 31; n++) {
          const bool table = n == 4 || n >= 29;
          const int q = n < 4 ? n : n - 1;
          const CUtensorMap* m = table ? &maps.e : n >= 25 ? &maps.g32 + p : &maps.g64 + p;
          const int c0 = table ? 0 : n >= 25 ? f_half : f_full + 64 * (q >> 3);
          const int c1 = table ? (2 * rb + ((n & 1) ^ 1)) * 128 + 64 * p : n >= 25 ? 128 * (n - 25) : 64 * (q & 7);
          const uint32_t fb = bars + 8 * (B_FA + (n & 3)), dst = sb + OFF_RING + (n & 3) * U + p * 8192;
          if (n < 4) mbar_wait(bars + 8 * (B_FE + n - 2), 0);
          else mbar_wait(bars + 8 * (B_EA + (n & 3)), ((n >> 2) & 1) ^ 1);
          tma2d(dst, m, fb, c0, c1);
          if (p == 0) mbar_expect_tx(fb, U);
        }
      } else if (warp == 15) {
        const unsigned ep1 = ld_x1(&ws->epoch[blockIdx.x * 8]) + 1;
        flag_wait(&ws->cntX[helper ? 0 : 32 * j], ep1 * 16u);
        PROF_EV(22);
        mbar_expect_tx(bars + 8 * B_HX, U);
        bulk_load(sb + OFF_XB, ws->X + (size_t)(helper ? 128 : kg * 8 + tn) * 8192, U, bars + 8 * B_HX);
        if (!helper) {
          flag_wait(&ws->cntT[32 * j], ep1 * 64u);
          PROF_EV(23);
          mbar_expect_tx(bars + 8 * B_TL, U);
          tma3d(sb + OFF_T, &maps.t, bars + 8 * B_TL, 64 * j, 0, 2 * rb);
#pragma unroll 1
          for (int i = 0; i < 3; i++) {
            flag_wait(&ws->cntP[32 * (rb * 8 + j) + i], ep1 * 8u);
            mbar_wait(bars + 8 * (B_PZ + (i == 0)), 0);
            if (i == 2) PROF_EV(26);
            mbar_expect_tx(bars + 8 * (B_HP + i), U);
            bulk_load(sb + (i ? (i - 1) * U : OFF_T), ws->part + (size_t)((rb * 8 + j) * 3 + i) * 1024, U, bars + 8 * (B_HP + i));
          }
          ws->epoch[blockIdx.x * 8] = ep1;
        }
      } else {
#pragma unroll 1
        for (int q = 4; q < 8; q++) xf_load(q);
        mbar_wait(bars + 8 * (B_FE + 2), 0);
        mbar_expect_tx(bars + 8 * B_E0, U);
        tma2d(sb + OFF_XB, &maps.e, bars + 8 * B_E0, 0, 2 * rb * 128);
        tma2d(sb + OFF_XB + 8192, &maps.e, bars + 8 * B_E0, 0, 2 * rb * 128 + 64);
#pragma unroll 1
        for (int h2 = 0; h2 < 2; h2++) {
          const int s0 = 2 * rb + h2, sg = (s0 & ~6) | ((s0 & 2) << 1) | ((s0 & 4) >> 1);
          mbar_wait(bars + 8 * (B_XS + h2), 0);
#pragma unroll 1
          for (int c = 0; c < 2; c++) {
            asm volatile("cp.async.bulk.tensor.4d.global.shared::cta.bulk_group [%0, {%2, %3, %4, %5}], [%1];" ::"l"(&maps.xs),
                         "r"(sb + OFF_XB + h2 * 8192 + c * 4096), "r"(0), "r"(sg), "r"(0), "r"(16 * j + 8 * c) : "memory");
            if (j == 0)
              asm volatile("cp.async.bulk.global.shared::cta.bulk_group [%0], [%1], 256;" ::"l"(ws->X + 128 * 8192 + c * 4096 + sg * 128),
                           "r"(sb + OFF_SP + h2 * 512 + c * 256) : "memory");
            if (SPACE && h2 + c < 2) __nanosleep(SPACE);
          }
        }
        bulk_done_signal(&ws->cntX[32 * j]);
        PROF_EV(20);
        if (rb < 8) asm volatile("cp.async.bulk.prefetch.tensor.2d.L2.global [%0, {%1, %2}];" ::"l"(&maps.g32 + (rb >> 2)), "r"(f_half), "r"(128 * (rb & 3)) : "memory");
        else asm volatile("cp.async.bulk.prefetch.tensor.2d.L2.global [%0, {%1, %2}];" ::"l"(&maps.d224), "r"(64 * (rb - 8)), "r"(224 * j) : "memory");
#pragma unroll 1
        for (int t = 0; t < 8; t++) {
          const int i = t < 3 ? t + 1 : t < 6 ? t - 2 : 0;
          const int col = 64 * (2 * ((q4 + i) & 3) + ((t < 3 || t == 6) ? 1 - rank : rank));
          const uint32_t fb = bars + 8 * (B_FT + (t & 3)), dst = sb + (t & 3) * TB;
          mbar_wait(bars + 8 * (B_ET + (t == 2 ? 3 : t & 3)), t >> 2);
          mbar_expect_tx(fb, TB);
          tma2d(dst, &maps.d224, fb, col, 224 * j);
          if (t < 2) mbar_wait(bars + 8 * (B_ET + t + 1), 0);
          tma2d(dst + 28672, &maps.ft, fb, col, 64 * j);
        }
      }
    }
  }
}

typedef CUresult (*EncodeFn)(CUtensorMap*, CUtensorMapDataType, cuuint32_t, void*, const cuuint64_t*, const cuuint64_t*, const cuuint32_t*,
                             const cuuint32_t*, CUtensorMapInterleave, CUtensorMapSwizzle, CUtensorMapL2promotion, CUtensorMapFloatOOBfill);

static void encode(EncodeFn f, CUtensorMap* m, const void* base, int rank, const cuuint64_t* dims, const cuuint64_t* strides, const cuuint32_t* box,
                   CUtensorMapSwizzle sw) {
  cuuint32_t es[5] = {1, 1, 1, 1, 1};
  f(m, CU_TENSOR_MAP_DATA_TYPE_BFLOAT16, rank, (void*)base, dims, strides, box, es, CU_TENSOR_MAP_INTERLEAVE_NONE, sw,
    CU_TENSOR_MAP_L2_PROMOTION_L2_128B, CU_TENSOR_MAP_FLOAT_OOB_FILL_NONE);
}

extern "C" void kernel_launch(void* const* d_in, const int* in_sizes, int n_in, void* d_out, int out_size) {
  (void)in_sizes; (void)n_in; (void)out_size;
  const __nv_bfloat16* x = (const __nv_bfloat16*)d_in[0];
  const __nv_bfloat16* w_r = (const __nv_bfloat16*)d_in[1];
  const __nv_bfloat16* w_i = (const __nv_bfloat16*)d_in[2];
  const __nv_bfloat16* Wg = (const __nv_bfloat16*)d_in[4];
  const __nv_bfloat16* Wu = (const __nv_bfloat16*)d_in[5];
  const __nv_bfloat16* Wd = (const __nv_bfloat16*)d_in[6];
  const __nv_bfloat16* gw = (const __nv_bfloat16*)d_in[7];

  void* fp = nullptr; cudaDriverEntryPointQueryResult qr;
  cudaGetDriverEntryPoint("cuTensorMapEncodeTiled", &fp, cudaEnableDefault, &qr);
  EncodeFn enc = (EncodeFn)fp;
  void *pFT, *pET, *pDT, *pW;
  cudaGetSymbolAddress(&pDT, g_DT); cudaGetSymbolAddress(&pW, g_work);
  void *pX = ((Work*)pW)->X, *pT = ((Work*)pW)->T;
  cudaGetSymbolAddress(&pFT, g_FT); cudaGetSymbolAddress(&pET, g_ET);

  Maps mp;
  const CUtensorMapSwizzle S128 = CU_TENSOR_MAP_SWIZZLE_128B, S64 = CU_TENSOR_MAP_SWIZZLE_64B;
  { cuuint64_t d[3] = {512, 64, 32}, s[2] = {32768, 1024}; cuuint32_t b[3] = {64, 64, 2}, b2[3] = {64, 16, 1};
    encode(enc, &mp.x, x, 3, d, s, b, S128); encode(enc, &mp.o, d_out, 3, d, s, b2, S128); }
  { cuuint64_t d[2] = {512, 512}, s[1] = {1024}; cuuint32_t b[2] = {64, 64}; encode(enc, &mp.ft, pFT, 2, d, s, b, S128); }
  { cuuint64_t d[4] = {128, 32, 2, 129}, s[3] = {256, 8192, 16384}; cuuint32_t b[4] = {128, 1, 2, 8}; encode(enc, &mp.xs, pX, 4, d, s, b, CU_TENSOR_MAP_SWIZZLE_NONE); }
  { cuuint64_t d[3] = {512, 32, 64}, s[2] = {65536, 1024}; cuuint32_t b[3] = {32, 32, 2}; encode(enc, &mp.ts, pT, 3, d, s, b, S64); }
  { cuuint64_t d[3] = {512, 64, 32}, s[2] = {1024, 65536}; cuuint32_t b[3] = {64, 64, 2}; encode(enc, &mp.t, pT, 3, d, s, b, S128); }
  { cuuint64_t d[2] = {64, 4096}, s[1] = {128}; cuuint32_t b[2] = {64, 64}; encode(enc, &mp.e, pET, 2, d, s, b, S128); }
  { cuuint64_t d[2] = {1792, 512}, s[1] = {3584}; cuuint32_t b[2] = {64, 64}, b2[2] = {32, 128};
    encode(enc, &mp.g64, Wg, 2, d, s, b, S128); encode(enc, &mp.u64, Wu, 2, d, s, b, S128);
    encode(enc, &mp.g32, Wg, 2, d, s, b2, S64); encode(enc, &mp.u32, Wu, 2, d, s, b2, S64); }
  { cuuint64_t d[2] = {512, 1792}, s[1] = {1024}; cuuint32_t b[2] = {64, 224}; encode(enc, &mp.d224, Wd, 2, d, s, b, S128); }
  { cuuint64_t d[4] = {264, 32, 8, 8}, s[3] = {32896, 512, 4112}; cuuint32_t b[4] = {24, 32, 2, 1};
    encode(enc, &mp.wr, w_r, 4, d, s, b, CU_TENSOR_MAP_SWIZZLE_NONE); encode(enc, &mp.wi, w_i, 4, d, s, b, CU_TENSOR_MAP_SWIZZLE_NONE); }

  cudaFuncSetAttribute(fused_kernel, cudaFuncAttributeMaxDynamicSharedMemorySize, SMEM_BYTES);
  fused_kernel<<<NCTA, 512, SMEM_BYTES>>>((Work*)pW, (const uint16_t*)pDT, w_r, w_i, gw, x, (const uint16_t*)pFT, Wg, Wu, mp);
}
```

```cpp
#include <cuda_runtime.h>
#include <cuda_bf16.h>
#include <cuda.h>
#include <stdint.h>

namespace tbl {
constexpr double PI = 3.14159265358979323846264338327950288;
constexpr double sin_s(double x) { double t = x, s = x; for (int n = 1; n < 12; n++) { t *= -x * x / ((2 * n) * (2 * n + 1)); s += t; } return s; }
constexpr double cos_s(double x) { double t = 1, s = 1; for (int n = 1; n < 12; n++) { t *= -x * x / ((2 * n - 1) * (2 * n)); s += t; } return s; }
constexpr double cos2048(int m) {
  m &= 2047; if (m > 1024) m = 2048 - m;
  bool neg = false; if (m > 512) { m = 1024 - m; neg = true; }
  double v = (m <= 256) ? cos_s(2 * PI * m / 2048) : sin_s(2 * PI * (512 - m) / 2048);
  return neg ? -v : v;
}
constexpr uint16_t to_bf16(double v) {
  if (v == 0) return 0;
  uint16_t s = 0; if (v < 0) { s = 0x8000; v = -v; }
  int e = 0; while (v >= 2) { v /= 2; e++; } while (v < 1) { v *= 2; e--; }
  double m = (v - 1) * 128; int mi = (int)m; double fr = m - mi;
  if (fr > 0.5 || (fr == 0.5 && (mi & 1))) mi++;
  if (mi == 128) { mi = 0; e++; }
  return (uint16_t)(s | ((e + 127) << 7) | mi);
}
struct CosT { uint16_t v[2048]; constexpr CosT() : v() { for (int i = 0; i < 2048; i++) v[i] = to_bf16(cos2048(i)); } };
struct alignas(1024) FT {
  uint16_t v[512 * 512];
  constexpr FT() : v() {
    CosT c;
    for (int r = 0; r < 512; r++) {
      int k = (r >> 4) * 8 + (r & 7), e = (r >> 3) & 1;
      int mul = 4 * k, add = e ? 512 : 0;
      if (k == 0 && e == 1) { mul = 1024; add = 0; }
      for (int d = 0; d < 512; d++) v[r * 512 + d] = c.v[(d * mul + add) & 2047];
    }
  }
};
struct alignas(1024) ET {
  uint16_t v[2048 * 128];
  constexpr ET() : v() {
    CosT c;
    for (int s = 0; s < 2048; s++)
      for (int j = 0; j < 64; j++) {
        const int o = (s & 31) * 8192 + (s >> 5) * 64 + j;
        v[o] = c.v[(s * j) & 2047]; v[o + 4096] = c.v[(s * j + 512) & 2047];
      }
  }
};
struct alignas(1024) DT {
  uint16_t v[64 * 64];
  constexpr DT() : v() {
    CosT c;
    for (int r = 0; r < 64; r++)
      for (int n = 0; n < 64; n++) {
        const int sg = r >> 1, s0 = (sg & ~6) | ((sg & 2) << 1) | ((sg & 4) >> 1), e = r & 1, f = n & 1;
        const int m = 64 * s0 * (n >> 1) + (e == f ? 0 : e ? -512 : 512);
        v[r * 64 + (((n >> 3) ^ (r & 7)) << 3) + (n & 7)] = c.v[m & 2047];
      }
  }
};
}

__device__ constexpr tbl::FT g_FT = tbl::FT();
__device__ constexpr tbl::ET g_ET = tbl::ET();
__device__ constexpr tbl::DT g_DT = tbl::DT();

struct alignas(1024) Work {
  unsigned epoch[132 * 8];
  unsigned cntX[8 * 32], cntT[8 * 32], cntP[128 * 32], cntW[32], cntH[32];
  alignas(16) float gate[16 * 128];
  alignas(16) uint2 Wh[2 * 2048];
  alignas(16) uint2 Ts[32 * 64];
  alignas(1024) uint16_t X[129 * 8192];
  alignas(1024) uint16_t T[32 * 64 * 512];
  alignas(1024) uint4 part[128 * 3 * 1024];
};
__device__ Work g_work;
#define PROF_EV(i) do {} while (0)
#define PROF_CK(i) do {} while (0)

__device__ __forceinline__ uint32_t smem_u32(const void* p) { return (uint32_t)__cvta_generic_to_shared(p); }
__device__ __forceinline__ void mbar_init(uint32_t bar, uint32_t cnt) { asm volatile("mbarrier.init.shared::cta.b64 [%0], %1;" ::"r"(bar), "r"(cnt)); }
__device__ __forceinline__ void mbar_expect_tx(uint32_t bar, uint32_t bytes) { asm volatile("mbarrier.arrive.expect_tx.shared::cta.b64 _, [%0], %1;" ::"r"(bar), "r"(bytes) : "memory"); }
__device__ __forceinline__ void mbar_arrive(uint32_t bar) { asm volatile("mbarrier.arrive.shared::cta.b64 _, [%0];" ::"r"(bar) : "memory"); }
__device__ __forceinline__ bool elect_one() {
  uint32_t p;
  asm volatile("{\n.reg .pred p;\nelect.sync _|p, 0xffffffff;\nselp.u32 %0, 1, 0, p;\n}" : "=r"(p));
  return p;
}
__device__ __forceinline__ void mbar_arrive_if(bool p, uint32_t bar) {
  asm volatile("{\n.reg .pred p;\nsetp.ne.b32 p, %1, 0;\n@p mbarrier.arrive.shared::cta.b64 _, [%0];\n}" ::"r"(bar), "r"((int)p) : "memory");
}
__device__ __forceinline__ void hint_add_if(bool p, unsigned* a) {
  asm volatile("{\n.reg .pred p;\nsetp.ne.b32 p, %1, 0;\n@p red.relaxed.gpu.global.add.u32 [%0], 1;\n}" ::"l"(a), "r"((int)p) : "memory");
}
__device__ __forceinline__ bool mbar_try(uint32_t bar, uint32_t parity) {
  uint32_t ok;
  asm volatile("{\n.reg .pred p;\nmbarrier.test_wait.parity.shared::cta.b64 p, [%1], %2;\nselp.u32 %0, 1, 0, p;\n}" : "=r"(ok) : "r"(bar), "r"(parity) : "memory");
  return ok;
}
__device__ __forceinline__ void mbar_wait(uint32_t bar, uint32_t parity) {
  asm volatile(
      "{\n.reg .pred p;\n.reg .u32 n;\nmov.u32 n, 0;\n"
      "W_LOOP:\nmbarrier.try_wait.parity.shared::cta.b64 p, [%0], %1;\n@p bra W_DONE;\n"
      "add.u32 n, n, 1;\nsetp.lt.u32 p, n, 0x40000;\n@p bra W_LOOP;\ntrap;\nW_DONE:\n}" ::"r"(bar), "r"(parity) : "memory");
}
__device__ __forceinline__ void bulk_load(uint32_t dst, const void* src, uint32_t bytes, uint32_t bar) {
  asm volatile("cp.async.bulk.shared::cluster.global.mbarrier::complete_tx::bytes [%0], [%1], %2, [%3];" ::"r"(dst), "l"(src), "r"(bytes), "r"(bar) : "memory");
}
__device__ __forceinline__ void cp16(uint32_t dst, const void* src) { asm volatile("cp.async.cg.shared.global [%0], [%1], 16;" ::"r"(dst), "l"(src) : "memory"); }
__device__ __forceinline__ void spin_guard(uint32_t t0) { if ((uint32_t)clock() - t0 > (1u << 30)) __trap(); }
__device__ __forceinline__ float tagf(float v, uint32_t tag) { return __uint_as_float((__float_as_uint(v) & ~1u) | tag); }
__device__ __forceinline__ float untag(float v) { return __uint_as_float(__float_as_uint(v) & ~1u); }
__device__ __forceinline__ void st_x2(float2* p, float a, float b) { asm volatile("st.relaxed.gpu.global.v2.f32 [%0], {%1,%2};" ::"l"(p), "f"(a), "f"(b) : "memory"); }
__device__ __forceinline__ float2 ld_x2(const float2* p) { float2 v; asm volatile("ld.relaxed.gpu.global.v2.f32 {%0,%1}, [%2];" : "=f"(v.x), "=f"(v.y) : "l"(p) : "memory"); return v; }
__device__ __forceinline__ void st_u2(uint2* p, uint32_t a, uint32_t b) { asm volatile("st.relaxed.gpu.global.v2.u32 [%0], {%1,%2};" ::"l"(p), "r"(a), "r"(b) : "memory"); }
__device__ __forceinline__ void prefetch2d(const CUtensorMap* m, int c0, int c1) { asm volatile("cp.async.bulk.prefetch.tensor.2d.L2.global [%0, {%1, %2}];" ::"l"(m), "r"(c0), "r"(c1) : "memory"); }
__device__ __forceinline__ void prefetch1d(const void* p, uint32_t bytes) { asm volatile("cp.async.bulk.prefetch.L2.global [%0], %1;" ::"l"(p), "r"(bytes) : "memory"); }
__device__ __forceinline__ uint32_t ld_x1(const void* p) { uint32_t v; asm volatile("ld.relaxed.gpu.global.u32 %0, [%1];" : "=r"(v) : "l"(p) : "memory"); return v; }
__device__ __forceinline__ uint4 ld_x4(const void* p) { uint4 v; asm volatile("ld.relaxed.gpu.global.v4.u32 {%0,%1,%2,%3}, [%4];" : "=r"(v.x), "=r"(v.y), "=r"(v.z), "=r"(v.w) : "l"(p) : "memory"); return v; }
__device__ __forceinline__ void st_x4(void* p, uint32_t a, uint32_t b, uint32_t c, uint32_t d) { asm volatile("st.relaxed.gpu.global.v4.u32 [%0], {%1,%2,%3,%4};" ::"l"(p), "r"(a), "r"(b), "r"(c), "r"(d) : "memory"); }
__device__ __forceinline__ uint32_t mapa(uint32_t a, uint32_t cta) { uint32_t r; asm volatile("mapa.shared::cluster.u32 %0, %1, %2;" : "=r"(r) : "r"(a), "r"(cta)); return r; }
__device__ __forceinline__ void stsm4t(uint32_t a, uint32_t r0, uint32_t r1, uint32_t r2, uint32_t r3) {
  asm volatile("stmatrix.sync.aligned.m8n8.x4.trans.shared.b16 [%0], {%1,%2,%3,%4};" ::"r"(a), "r"(r0), "r"(r1), "r"(r2), "r"(r3) : "memory");
}
__device__ __forceinline__ void hint_add(unsigned* p) { asm volatile("red.relaxed.gpu.global.add.u32 [%0], 1;" ::"l"(p) : "memory"); }
__device__ __forceinline__ void hint_wait(const unsigned* p, unsigned target) {
  const uint32_t t0 = (uint32_t)clock();
  while ((int)(ld_x1(p) - target) < 0) spin_guard(t0);
}
__device__ __forceinline__ void bulk_done_signal(unsigned* p) {
  asm volatile("cp.async.bulk.commit_group;\ncp.async.bulk.wait_group 0;\nfence.proxy.async.global;" ::: "memory");
  hint_add(p);
}
__device__ __forceinline__ void flag_wait(const unsigned* p, unsigned target) {
  hint_wait(p, target);
  asm volatile("fence.proxy.async.global;" ::: "memory");
}
__device__ __forceinline__ void tma2d(uint32_t dst, const CUtensorMap* m, uint32_t bar, int c0, int c1) {
  asm volatile("cp.async.bulk.tensor.2d.shared::cluster.global.mbarrier::complete_tx::bytes [%0], [%1, {%3, %4}], [%2];" ::"r"(dst), "l"(m), "r"(bar), "r"(c0), "r"(c1) : "memory");
}
__device__ __forceinline__ void tma3d(uint32_t dst, const CUtensorMap* m, uint32_t bar, int c0, int c1, int c2) {
  asm volatile("cp.async.bulk.tensor.3d.shared::cluster.global.mbarrier::complete_tx::bytes [%0], [%1, {%3, %4, %5}], [%2];" ::"r"(dst), "l"(m), "r"(bar), "r"(c0), "r"(c1), "r"(c2) : "memory");
}
__device__ __forceinline__ void tma4d(uint32_t dst, const CUtensorMap* m, uint32_t bar, int c0, int c1, int c2, int c3) {
  asm volatile("cp.async.bulk.tensor.4d.shared::cluster.global.mbarrier::complete_tx::bytes [%0], [%1, {%3, %4, %5, %6}], [%2];" ::"r"(dst), "l"(m), "r"(bar), "r"(c0), "r"(c1), "r"(c2), "r"(c3) : "memory");
}
__device__ __forceinline__ void wg_fence() { asm volatile("wgmma.fence.sync.aligned;" ::: "memory"); }
__device__ __forceinline__ void wg_commit() { asm volatile("wgmma.commit_group.sync.aligned;" ::: "memory"); }
template <int N> __device__ __forceinline__ void wg_wait() { asm volatile("wgmma.wait_group.sync.aligned %0;" ::"n"(N) : "memory"); }
template <int O, int N, int NN> __device__ __forceinline__ void fence_regs(float (&d)[NN]) {
#pragma unroll
  for (int i = 0; i < N; i++) asm volatile("" : "+f"(d[O + i])::"memory");
}
__device__ __forceinline__ uint32_t pack_bf16(float lo, float hi) {
  uint32_t r; asm("cvt.rn.bf16x2.f32 %0, %1, %2;" : "=r"(r) : "f"(hi), "f"(lo)); return r;
}
__device__ __forceinline__ uint32_t pack_pin(float lo, float hi) {
  uint32_t r; asm volatile("cvt.rn.bf16x2.f32 %0, %1, %2;" : "=r"(r) : "f"(hi), "f"(lo) : "memory"); return r;
}
__device__ __forceinline__ float bf_lo(uint32_t u) { return __uint_as_float(u << 16); }
__device__ __forceinline__ float bf_hi(uint32_t u) { return __uint_as_float(u & 0xffff0000u); }

__device__ __forceinline__ uint64_t d128(uint32_t lo) { uint64_t d; asm("mov.b64 %0, {%1, 0x40000040};" : "=l"(d) : "r"(lo)); return d; }
__device__ __forceinline__ uint64_t d64(uint32_t lo) { uint64_t d; asm("mov.b64 %0, {%1, 0x80000020};" : "=l"(d) : "r"(lo)); return d; }
template<int O,int TB,int ACC,int NN> __device__ __forceinline__ void mma_ss64(float (&d)[NN], uint64_t da, uint64_t db, int sd = 0){
  if constexpr (ACC == 1) asm volatile("wgmma.mma_async.sync.aligned.m64n64k16.f32.bf16.bf16 {%0,%1,%2,%3,%4,%5,%6,%7,%8,%9,%10,%11,%12,%13,%14,%15,%16,%17,%18,%19,%20,%21,%22,%23,%24,%25,%26,%27,%28,%29,%30,%31}, %32, %33, 1, 1, 1, %35, %34;"
   : "+f"(d[O+0]), "+f"(d[O+1]), "+f"(d[O+2]), "+f"(d[O+3]), "+f"(d[O+4]), "+f"(d[O+5]), "+f"(d[O+6]), "+f"(d[O+7]), "+f"(d[O+8]), "+f"(d[O+9]), "+f"(d[O+10]), "+f"(d[O+11]), "+f"(d[O+12]), "+f"(d[O+13]), "+f"(d[O+14]), "+f"(d[O+15]), "+f"(d[O+16]), "+f"(d[O+17]), "+f"(d[O+18]), "+f"(d[O+19]), "+f"(d[O+20]), "+f"(d[O+21]), "+f"(d[O+22]), "+f"(d[O+23]), "+f"(d[O+24]), "+f"(d[O+25]), "+f"(d[O+26]), "+f"(d[O+27]), "+f"(d[O+28]), "+f"(d[O+29]), "+f"(d[O+30]), "+f"(d[O+31])
   : "l"(da), "l"(db), "n"(TB & 1), "n"(TB >> 1));
  else if constexpr (ACC == 0) asm volatile("wgmma.mma_async.sync.aligned.m64n64k16.f32.bf16.bf16 {%0,%1,%2,%3,%4,%5,%6,%7,%8,%9,%10,%11,%12,%13,%14,%15,%16,%17,%18,%19,%20,%21,%22,%23,%24,%25,%26,%27,%28,%29,%30,%31}, %32, %33, 0, 1, 1, %35, %34;"
   : "=f"(d[O+0]), "=f"(d[O+1]), "=f"(d[O+2]), "=f"(d[O+3]), "=f"(d[O+4]), "=f"(d[O+5]), "=f"(d[O+6]), "=f"(d[O+7]), "=f"(d[O+8]), "=f"(d[O+9]), "=f"(d[O+10]), "=f"(d[O+11]), "=f"(d[O+12]), "=f"(d[O+13]), "=f"(d[O+14]), "=f"(d[O+15]), "=f"(d[O+16]), "=f"(d[O+17]), "=f"(d[O+18]), "=f"(d[O+19]), "=f"(d[O+20]), "=f"(d[O+21]), "=f"(d[O+22]), "=f"(d[O+23]), "=f"(d[O+24]), "=f"(d[O+25]), "=f"(d[O+26]), "=f"(d[O+27]), "=f"(d[O+28]), "=f"(d[O+29]), "=f"(d[O+30]), "=f"(d[O+31])
   : "l"(da), "l"(db), "n"(TB & 1), "n"(TB >> 1));
  else asm volatile("{\n.reg .pred p;\nsetp.ne.b32 p, %36, 0;\nwgmma.mma_async.sync.aligned.m64n64k16.f32.bf16.bf16 {%0,%1,%2,%3,%4,%5,%6,%7,%8,%9,%10,%11,%12,%13,%14,%15,%16,%17,%18,%19,%20,%21,%22,%23,%24,%25,%26,%27,%28,%29,%30,%31}, %32, %33, p, 1, 1, %35, %34;\n}"
   : "+f"(d[O+0]), "+f"(d[O+1]), "+f"(d[O+2]), "+f"(d[O+3]), "+f"(d[O+4]), "+f"(d[O+5]), "+f"(d[O+6]), "+f"(d[O+7]), "+f"(d[O+8]), "+f"(d[O+9]), "+f"(d[O+10]), "+f"(d[O+11]), "+f"(d[O+12]), "+f"(d[O+13]), "+f"(d[O+14]), "+f"(d[O+15]), "+f"(d[O+16]), "+f"(d[O+17]), "+f"(d[O+18]), "+f"(d[O+19]), "+f"(d[O+20]), "+f"(d[O+21]), "+f"(d[O+22]), "+f"(d[O+23]), "+f"(d[O+24]), "+f"(d[O+25]), "+f"(d[O+26]), "+f"(d[O+27]), "+f"(d[O+28]), "+f"(d[O+29]), "+f"(d[O+30]), "+f"(d[O+31])
   : "l"(da), "l"(db), "n"(TB & 1), "n"(TB >> 1), "r"(sd));
}
template<int O,int TB,int ACC,int NN> __device__ __forceinline__ void mma_rs64(float (&d)[NN], uint32_t a0, uint32_t a1, uint32_t a2, uint32_t a3, uint64_t db, int sd = 0){
  if constexpr (ACC == 1) asm volatile("wgmma.mma_async.sync.aligned.m64n64k16.f32.bf16.bf16 {%0,%1,%2,%3,%4,%5,%6,%7,%8,%9,%10,%11,%12,%13,%14,%15,%16,%17,%18,%19,%20,%21,%22,%23,%24,%25,%26,%27,%28,%29,%30,%31}, {%32,%33,%34,%35}, %36, 1, 1, 1, %37;"
   : "+f"(d[O+0]), "+f"(d[O+1]), "+f"(d[O+2]), "+f"(d[O+3]), "+f"(d[O+4]), "+f"(d[O+5]), "+f"(d[O+6]), "+f"(d[O+7]), "+f"(d[O+8]), "+f"(d[O+9]), "+f"(d[O+10]), "+f"(d[O+11]), "+f"(d[O+12]), "+f"(d[O+13]), "+f"(d[O+14]), "+f"(d[O+15]), "+f"(d[O+16]), "+f"(d[O+17]), "+f"(d[O+18]), "+f"(d[O+19]), "+f"(d[O+20]), "+f"(d[O+21]), "+f"(d[O+22]), "+f"(d[O+23]), "+f"(d[O+24]), "+f"(d[O+25]), "+f"(d[O+26]), "+f"(d[O+27]), "+f"(d[O+28]), "+f"(d[O+29]), "+f"(d[O+30]), "+f"(d[O+31])
   : "r"(a0), "r"(a1), "r"(a2), "r"(a3), "l"(db), "n"(TB));
  else if constexpr (ACC == 0) asm volatile("wgmma.mma_async.sync.aligned.m64n64k16.f32.bf16.bf16 {%0,%1,%2,%3,%4,%5,%6,%7,%8,%9,%10,%11,%12,%13,%14,%15,%16,%17,%18,%19,%20,%21,%22,%23,%24,%25,%26,%27,%28,%29,%30,%31}, {%32,%33,%34,%35}, %36, 0, 1, 1, %37;"
   : "=f"(d[O+0]), "=f"(d[O+1]), "=f"(d[O+2]), "=f"(d[O+3]), "=f"(d[O+4]), "=f"(d[O+5]), "=f"(d[O+6]), "=f"(d[O+7]), "=f"(d[O+8]), "=f"(d[O+9]), "=f"(d[O+10]), "=f"(d[O+11]), "=f"(d[O+12]), "=f"(d[O+13]), "=f"(d[O+14]), "=f"(d[O+15]), "=f"(d[O+16]), "=f"(d[O+17]), "=f"(d[O+18]), "=f"(d[O+19]), "=f"(d[O+20]), "=f"(d[O+21]), "=f"(d[O+22]), "=f"(d[O+23]), "=f"(d[O+24]), "=f"(d[O+25]), "=f"(d[O+26]), "=f"(d[O+27]), "=f"(d[O+28]), "=f"(d[O+29]), "=f"(d[O+30]), "=f"(d[O+31])
   : "r"(a0), "r"(a1), "r"(a2), "r"(a3), "l"(db), "n"(TB));
  else asm volatile("{\n.reg .pred p;\nsetp.ne.b32 p, %38, 0;\nwgmma.mma_async.sync.aligned.m64n64k16.f32.bf16.bf16 {%0,%1,%2,%3,%4,%5,%6,%7,%8,%9,%10,%11,%12,%13,%14,%15,%16,%17,%18,%19,%20,%21,%22,%23,%24,%25,%26,%27,%28,%29,%30,%31}, {%32,%33,%34,%35}, %36, p, 1, 1, %37;\n}"
   : "+f"(d[O+0]), "+f"(d[O+1]), "+f"(d[O+2]), "+f"(d[O+3]), "+f"(d[O+4]), "+f"(d[O+5]), "+f"(d[O+6]), "+f"(d[O+7]), "+f"(d[O+8]), "+f"(d[O+9]), "+f"(d[O+10]), "+f"(d[O+11]), "+f"(d[O+12]), "+f"(d[O+13]), "+f"(d[O+14]), "+f"(d[O+15]), "+f"(d[O+16]), "+f"(d[O+17]), "+f"(d[O+18]), "+f"(d[O+19]), "+f"(d[O+20]), "+f"(d[O+21]), "+f"(d[O+22]), "+f"(d[O+23]), "+f"(d[O+24]), "+f"(d[O+25]), "+f"(d[O+26]), "+f"(d[O+27]), "+f"(d[O+28]), "+f"(d[O+29]), "+f"(d[O+30]), "+f"(d[O+31])
   : "r"(a0), "r"(a1), "r"(a2), "r"(a3), "l"(db), "n"(TB), "r"(sd));
}
template<int O,int TB,int ACC,int NN> __device__ __forceinline__ void mma_ss128(float (&d)[NN], uint64_t da, uint64_t db, int sd = 0){
  if constexpr (ACC == 1) asm volatile("wgmma.mma_async.sync.aligned.m64n128k16.f32.bf16.bf16 {%0,%1,%2,%3,%4,%5,%6,%7,%8,%9,%10,%11,%12,%13,%14,%15,%16,%17,%18,%19,%20,%21,%22,%23,%24,%25,%26,%27,%28,%29,%30,%31,%32,%33,%34,%35,%36,%37,%38,%39,%40,%41,%42,%43,%44,%45,%46,%47,%48,%49,%50,%51,%52,%53,%54,%55,%56,%57,%58,%59,%60,%61,%62,%63}, %64, %65, 1, 1, 1, %67, %66;"
   : "+f"(d[O+0]), "+f"(d[O+1]), "+f"(d[O+2]), "+f"(d[O+3]), "+f"(d[O+4]), "+f"(d[O+5]), "+f"(d[O+6]), "+f"(d[O+7]), "+f"(d[O+8]), "+f"(d[O+9]), "+f"(d[O+10]), "+f"(d[O+11]), "+f"(d[O+12]), "+f"(d[O+13]), "+f"(d[O+14]), "+f"(d[O+15]), "+f"(d[O+16]), "+f"(d[O+17]), "+f"(d[O+18]), "+f"(d[O+19]), "+f"(d[O+20]), "+f"(d[O+21]), "+f"(d[O+22]), "+f"(d[O+23]), "+f"(d[O+24]), "+f"(d[O+25]), "+f"(d[O+26]), "+f"(d[O+27]), "+f"(d[O+28]), "+f"(d[O+29]), "+f"(d[O+30]), "+f"(d[O+31]), "+f"(d[O+32]), "+f"(d[O+33]), "+f"(d[O+34]), "+f"(d[O+35]), "+f"(d[O+36]), "+f"(d[O+37]), "+f"(d[O+38]), "+f"(d[O+39]), "+f"(d[O+40]), "+f"(d[O+41]), "+f"(d[O+42]), "+f"(d[O+43]), "+f"(d[O+44]), "+f"(d[O+45]), "+f"(d[O+46]), "+f"(d[O+47]), "+f"(d[O+48]), "+f"(d[O+49]), "+f"(d[O+50]), "+f"(d[O+51]), "+f"(d[O+52]), "+f"(d[O+53]), "+f"(d[O+54]), "+f"(d[O+55]), "+f"(d[O+56]), "+f"(d[O+57]), "+f"(d[O+58]), "+f"(d[O+59]), "+f"(d[O+60]), "+f"(d[O+61]), "+f"(d[O+62]), "+f"(d[O+63])
   : "l"(da), "l"(db), "n"(TB & 1), "n"(TB >> 1));
  else if constexpr (ACC == 0) asm volatile("wgmma.mma_async.sync.aligned.m64n128k16.f32.bf16.bf16 {%0,%1,%2,%3,%4,%5,%6,%7,%8,%9,%10,%11,%12,%13,%14,%15,%16,%17,%18,%19,%20,%21,%22,%23,%24,%25,%26,%27,%28,%29,%30,%31,%32,%33,%34,%35,%36,%37,%38,%39,%40,%41,%42,%43,%44,%45,%46,%47,%48,%49,%50,%51,%52,%53,%54,%55,%56,%57,%58,%59,%60,%61,%62,%63}, %64, %65, 0, 1, 1, %67, %66;"
   : "=f"(d[O+0]), "=f"(d[O+1]), "=f"(d[O+2]), "=f"(d[O+3]), "=f"(d[O+4]), "=f"(d[O+5]), "=f"(d[O+6]), "=f"(d[O+7]), "=f"(d[O+8]), "=f"(d[O+9]), "=f"(d[O+10]), "=f"(d[O+11]), "=f"(d[O+12]), "=f"(d[O+13]), "=f"(d[O+14]), "=f"(d[O+15]), "=f"(d[O+16]), "=f"(d[O+17]), "=f"(d[O+18]), "=f"(d[O+19]), "=f"(d[O+20]), "=f"(d[O+21]), "=f"(d[O+22]), "=f"(d[O+23]), "=f"(d[O+24]), "=f"(d[O+25]), "=f"(d[O+26]), "=f"(d[O+27]), "=f"(d[O+28]), "=f"(d[O+29]), "=f"(d[O+30]), "=f"(d[O+31]), "=f"(d[O+32]), "=f"(d[O+33]), "=f"(d[O+34]), "=f"(d[O+35]), "=f"(d[O+36]), "=f"(d[O+37]), "=f"(d[O+38]), "=f"(d[O+39]), "=f"(d[O+40]), "=f"(d[O+41]), "=f"(d[O+42]), "=f"(d[O+43]), "=f"(d[O+44]), "=f"(d[O+45]), "=f"(d[O+46]), "=f"(d[O+47]), "=f"(d[O+48]), "=f"(d[O+49]), "=f"(d[O+50]), "=f"(d[O+51]), "=f"(d[O+52]), "=f"(d[O+53]), "=f"(d[O+54]), "=f"(d[O+55]), "=f"(d[O+56]), "=f"(d[O+57]), "=f"(d[O+58]), "=f"(d[O+59]), "=f"(d[O+60]), "=f"(d[O+61]), "=f"(d[O+62]), "=f"(d[O+63])
   : "l"(da), "l"(db), "n"(TB & 1), "n"(TB >> 1));
  else asm volatile("{\n.reg .pred p;\nsetp.ne.b32 p, %68, 0;\nwgmma.mma_async.sync.aligned.m64n128k16.f32.bf16.bf16 {%0,%1,%2,%3,%4,%5,%6,%7,%8,%9,%10,%11,%12,%13,%14,%15,%16,%17,%18,%19,%20,%21,%22,%23,%24,%25,%26,%27,%28,%29,%30,%31,%32,%33,%34,%35,%36,%37,%38,%39,%40,%41,%42,%43,%44,%45,%46,%47,%48,%49,%50,%51,%52,%53,%54,%55,%56,%57,%58,%59,%60,%61,%62,%63}, %64, %65, p, 1, 1, %67, %66;\n}"
   : "+f"(d[O+0]), "+f"(d[O+1]), "+f"(d[O+2]), "+f"(d[O+3]), "+f"(d[O+4]), "+f"(d[O+5]), "+f"(d[O+6]), "+f"(d[O+7]), "+f"(d[O+8]), "+f"(d[O+9]), "+f"(d[O+10]), "+f"(d[O+11]), "+f"(d[O+12]), "+f"(d[O+13]), "+f"(d[O+14]), "+f"(d[O+15]), "+f"(d[O+16]), "+f"(d[O+17]), "+f"(d[O+18]), "+f"(d[O+19]), "+f"(d[O+20]), "+f"(d[O+21]), "+f"(d[O+22]), "+f"(d[O+23]), "+f"(d[O+24]), "+f"(d[O+25]), "+f"(d[O+26]), "+f"(d[O+27]), "+f"(d[O+28]), "+f"(d[O+29]), "+f"(d[O+30]), "+f"(d[O+31]), "+f"(d[O+32]), "+f"(d[O+33]), "+f"(d[O+34]), "+f"(d[O+35]), "+f"(d[O+36]), "+f"(d[O+37]), "+f"(d[O+38]), "+f"(d[O+39]), "+f"(d[O+40]), "+f"(d[O+41]), "+f"(d[O+42]), "+f"(d[O+43]), "+f"(d[O+44]), "+f"(d[O+45]), "+f"(d[O+46]), "+f"(d[O+47]), "+f"(d[O+48]), "+f"(d[O+49]), "+f"(d[O+50]), "+f"(d[O+51]), "+f"(d[O+52]), "+f"(d[O+53]), "+f"(d[O+54]), "+f"(d[O+55]), "+f"(d[O+56]), "+f"(d[O+57]), "+f"(d[O+58]), "+f"(d[O+59]), "+f"(d[O+60]), "+f"(d[O+61]), "+f"(d[O+62]), "+f"(d[O+63])
   : "l"(da), "l"(db), "n"(TB & 1), "n"(TB >> 1), "r"(sd));
}
template<int O,int TB,int ACC,int NN> __device__ __forceinline__ void mma_rs128(float (&d)[NN], uint32_t a0, uint32_t a1, uint32_t a2, uint32_t a3, uint64_t db, int sd = 0){
  if constexpr (ACC == 1) asm volatile("wgmma.mma_async.sync.aligned.m64n128k16.f32.bf16.bf16 {%0,%1,%2,%3,%4,%5,%6,%7,%8,%9,%10,%11,%12,%13,%14,%15,%16,%17,%18,%19,%20,%21,%22,%23,%24,%25,%26,%27,%28,%29,%30,%31,%32,%33,%34,%35,%36,%37,%38,%39,%40,%41,%42,%43,%44,%45,%46,%47,%48,%49,%50,%51,%52,%53,%54,%55,%56,%57,%58,%59,%60,%61,%62,%63}, {%64,%65,%66,%67}, %68, 1, 1, 1, %69;"
   : "+f"(d[O+0]), "+f"(d[O+1]), "+f"(d[O+2]), "+f"(d[O+3]), "+f"(d[O+4]), "+f"(d[O+5]), "+f"(d[O+6]), "+f"(d[O+7]), "+f"(d[O+8]), "+f"(d[O+9]), "+f"(d[O+10]), "+f"(d[O+11]), "+f"(d[O+12]), "+f"(d[O+13]), "+f"(d[O+14]), "+f"(d[O+15]), "+f"(d[O+16]), "+f"(d[O+17]), "+f"(d[O+18]), "+f"(d[O+19]), "+f"(d[O+20]), "+f"(d[O+21]), "+f"(d[O+22]), "+f"(d[O+23]), "+f"(d[O+24]), "+f"(d[O+25]), "+f"(d[O+26]), "+f"(d[O+27]), "+f"(d[O+28]), "+f"(d[O+29]), "+f"(d[O+30]), "+f"(d[O+31]), "+f"(d[O+32]), "+f"(d[O+33]), "+f"(d[O+34]), "+f"(d[O+35]), "+f"(d[O+36]), "+f"(d[O+37]), "+f"(d[O+38]), "+f"(d[O+39]), "+f"(d[O+40]), "+f"(d[O+41]), "+f"(d[O+42]), "+f"(d[O+43]), "+f"(d[O+44]), "+f"(d[O+45]), "+f"(d[O+46]), "+f"(d[O+47]), "+f"(d[O+48]), "+f"(d[O+49]), "+f"(d[O+50]), "+f"(d[O+51]), "+f"(d[O+52]), "+f"(d[O+53]), "+f"(d[O+54]), "+f"(d[O+55]), "+f"(d[O+56]), "+f"(d[O+57]), "+f"(d[O+58]), "+f"(d[O+59]), "+f"(d[O+60]), "+f"(d[O+61]), "+f"(d[O+62]), "+f"(d[O+63])
   : "r"(a0), "r"(a1), "r"(a2), "r"(a3), "l"(db), "n"(TB));
  else if constexpr (ACC == 0) asm volatile("wgmma.mma_async.sync.aligned.m64n128k16.f32.bf16.bf16 {%0,%1,%2,%3,%4,%5,%6,%7,%8,%9,%10,%11,%12,%13,%14,%15,%16,%17,%18,%19,%20,%21,%22,%23,%24,%25,%26,%27,%28,%29,%30,%31,%32,%33,%34,%35,%36,%37,%38,%39,%40,%41,%42,%43,%44,%45,%46,%47,%48,%49,%50,%51,%52,%53,%54,%55,%56,%57,%58,%59,%60,%61,%62,%63}, {%64,%65,%66,%67}, %68, 0, 1, 1, %69;"
   : "=f"(d[O+0]), "=f"(d[O+1]), "=f"(d[O+2]), "=f"(d[O+3]), "=f"(d[O+4]), "=f"(d[O+5]), "=f"(d[O+6]), "=f"(d[O+7]), "=f"(d[O+8]), "=f"(d[O+9]), "=f"(d[O+10]), "=f"(d[O+11]), "=f"(d[O+12]), "=f"(d[O+13]), "=f"(d[O+14]), "=f"(d[O+15]), "=f"(d[O+16]), "=f"(d[O+17]), "=f"(d[O+18]), "=f"(d[O+19]), "=f"(d[O+20]), "=f"(d[O+21]), "=f"(d[O+22]), "=f"(d[O+23]), "=f"(d[O+24]), "=f"(d[O+25]), "=f"(d[O+26]), "=f"(d[O+27]), "=f"(d[O+28]), "=f"(d[O+29]), "=f"(d[O+30]), "=f"(d[O+31]), "=f"(d[O+32]), "=f"(d[O+33]), "=f"(d[O+34]), "=f"(d[O+35]), "=f"(d[O+36]), "=f"(d[O+37]), "=f"(d[O+38]), "=f"(d[O+39]), "=f"(d[O+40]), "=f"(d[O+41]), "=f"(d[O+42]), "=f"(d[O+43]), "=f"(d[O+44]), "=f"(d[O+45]), "=f"(d[O+46]), "=f"(d[O+47]), "=f"(d[O+48]), "=f"(d[O+49]), "=f"(d[O+50]), "=f"(d[O+51]), "=f"(d[O+52]), "=f"(d[O+53]), "=f"(d[O+54]), "=f"(d[O+55]), "=f"(d[O+56]), "=f"(d[O+57]), "=f"(d[O+58]), "=f"(d[O+59]), "=f"(d[O+60]), "=f"(d[O+61]), "=f"(d[O+62]), "=f"(d[O+63])
   : "r"(a0), "r"(a1), "r"(a2), "r"(a3), "l"(db), "n"(TB));
  else asm volatile("{\n.reg .pred p;\nsetp.ne.b32 p, %70, 0;\nwgmma.mma_async.sync.aligned.m64n128k16.f32.bf16.bf16 {%0,%1,%2,%3,%4,%5,%6,%7,%8,%9,%10,%11,%12,%13,%14,%15,%16,%17,%18,%19,%20,%21,%22,%23,%24,%25,%26,%27,%28,%29,%30,%31,%32,%33,%34,%35,%36,%37,%38,%39,%40,%41,%42,%43,%44,%45,%46,%47,%48,%49,%50,%51,%52,%53,%54,%55,%56,%57,%58,%59,%60,%61,%62,%63}, {%64,%65,%66,%67}, %68, p, 1, 1, %69;\n}"
   : "+f"(d[O+0]), "+f"(d[O+1]), "+f"(d[O+2]), "+f"(d[O+3]), "+f"(d[O+4]), "+f"(d[O+5]), "+f"(d[O+6]), "+f"(d[O+7]), "+f"(d[O+8]), "+f"(d[O+9]), "+f"(d[O+10]), "+f"(d[O+11]), "+f"(d[O+12]), "+f"(d[O+13]), "+f"(d[O+14]), "+f"(d[O+15]), "+f"(d[O+16]), "+f"(d[O+17]), "+f"(d[O+18]), "+f"(d[O+19]), "+f"(d[O+20]), "+f"(d[O+21]), "+f"(d[O+22]), "+f"(d[O+23]), "+f"(d[O+24]), "+f"(d[O+25]), "+f"(d[O+26]), "+f"(d[O+27]), "+f"(d[O+28]), "+f"(d[O+29]), "+f"(d[O+30]), "+f"(d[O+31]), "+f"(d[O+32]), "+f"(d[O+33]), "+f"(d[O+34]), "+f"(d[O+35]), "+f"(d[O+36]), "+f"(d[O+37]), "+f"(d[O+38]), "+f"(d[O+39]), "+f"(d[O+40]), "+f"(d[O+41]), "+f"(d[O+42]), "+f"(d[O+43]), "+f"(d[O+44]), "+f"(d[O+45]), "+f"(d[O+46]), "+f"(d[O+47]), "+f"(d[O+48]), "+f"(d[O+49]), "+f"(d[O+50]), "+f"(d[O+51]), "+f"(d[O+52]), "+f"(d[O+53]), "+f"(d[O+54]), "+f"(d[O+55]), "+f"(d[O+56]), "+f"(d[O+57]), "+f"(d[O+58]), "+f"(d[O+59]), "+f"(d[O+60]), "+f"(d[O+61]), "+f"(d[O+62]), "+f"(d[O+63])
   : "r"(a0), "r"(a1), "r"(a2), "r"(a3), "l"(db), "n"(TB), "r"(sd));
}

#define NEARLY 0
#define XAHEAD 3
#define HEADN 6
#define WBATCH 1
#define WB 8
#define WSLEEP 20
#define XSPREAD 4
#define NOSEND 0
#define MSPLIT 3
#define PFALL 1
#define L2PF 1
#define STAG 0
#define EPF 2
#define XNB 2
#define FNB 0
#define GNB 0
#define TH 4
#define SPACE 40
#define WPF 1
#define WAFTER 7
#define WPACE 0
#define GATE_AT 4
#define TPACE 40
#define PFMODE 0
#define MAPMODE 1
template <int V> struct IC { static constexpr int value = V; };
struct Maps { CUtensorMap x, ft, g64, u64, e, wr, wi, xs, ts, t, g32, u32, d224, o; };

constexpr int NCTA = 130;
constexpr int U = 16384;
constexpr int TB = 36864;
constexpr int OFF_RING = 8 * U, OFF_Z = 9 * U, OFF_XB = 12 * U, OFF_T = 13 * U, OFF_D = OFF_T;
constexpr int OFF_BAR = 14 * U, OFF_SP = OFF_BAR + 512, OFF_G = OFF_SP + 1024 + 128;
constexpr int SMEM_BYTES = OFF_G + 512;
constexpr int B_FX = 0, B_FA = 8, B_FT = 12, B_Z = 16, B_W = 24, B_HX = 25, B_TL = 26, B_HP = 27, B_WR = 30, B_E0 = 34;
constexpr int B_EA = 35, B_ET = 39, B_PZ = 43, B_RDY = 45, B_FE = 46;
constexpr int B_T = 50, B_XS = 51, B_G = 53, NBAR = 54;
__host__ __device__ constexpr int rslot(int n) { return n & 3; }
__host__ __device__ constexpr int rpar(int n) { return (n >> 2) & 1; }

__global__ void __cluster_dims__(2, 1, 1) __launch_bounds__(512, 1)
fused_kernel(Work* __restrict__ ws, const uint16_t* __restrict__ dtab, const __nv_bfloat16* __restrict__ w_r, const __nv_bfloat16* __restrict__ w_i,
             const __nv_bfloat16* __restrict__ gate_w, const __nv_bfloat16* __restrict__ x, const uint16_t* __restrict__ ftab,
             const __nv_bfloat16* __restrict__ Wg, const __nv_bfloat16* __restrict__ Wu, const __grid_constant__ Maps maps) {
  extern __shared__ __align__(1024) uint8_t smem[];
  const uint32_t sb = smem_u32(smem);
  const uint32_t bars = sb + OFF_BAR;
  const int tid = threadIdx.x, lane = tid & 31;
  const int warp = __shfl_sync(0xffffffffu, tid >> 5, 0);
  const bool helper = blockIdx.x >= 128;
  const int cl = (blockIdx.x >> 1) & 63, rank = blockIdx.x & 1;
  const int q4 = (cl & 1) | ((cl >> 2) & 2), rb = ((cl >> 1) & 3) | ((cl >> 4) << 2);
  const int j = 2 * q4 + rank;
  const int f_full = 448 * q4 + (rank ? 256 : 0);
  const int f_half = 448 * q4 + (rank ? 224 : 192);
  const int kg = 2 * j + (rb >> 3), tn = rb & 7;

  if (tid == 64) { PROF_EV(0); PROF_CK(40); }
  if (warp < 8) {
    if (!helper) {
      if (tid < 16 * XNB) {
        const int r = 16 * j + (tid & 15);
        asm volatile("prefetch.global.L2 [%0];" ::"l"(x + (size_t)(2 * rb + (r >> 6) + 32 * (r & 63)) * 512 + 64 * (tid >> 4)));
      } else if (tid >= 128 && tid < 128 + 4 * FNB) {
        asm volatile("prefetch.global.L2 [%0];" ::"l"(ftab + (64 * j + 4 * rb + (tid & 3)) * 512 + 64 * ((tid - 128) >> 2)));
      } else if (tid >= 192 && tid < 192 + 8 * GNB) {
        asm volatile("prefetch.global.L2 [%0];" ::"l"(((tid & 4) ? Wu : Wg) + (size_t)(64 * ((tid - 192) >> 3) + 4 * rb + (tid & 3)) * 1792 + f_full));
      }
    }
    asm volatile("barrier.cluster.arrive.relaxed.aligned;" ::: "memory");
    asm volatile("setmaxnreg.inc.sync.aligned.u32 192;");
    if (!helper) {
      const int wg = warp >> 2, w = warp & 3, g = lane >> 2;
      const bool elect = (tid & 127) == 0;
      float cX[32], cA[64], cB[64], cC[64], ci[64], ct[64];
      const int zero = blockIdx.x >> 16;
      uint32_t h[56], yf[16];
      const uint32_t d0 = (sb & 0x3FFFF) >> 4;
      const uint32_t dK = d0 | (1u << 16), dN = d0 | (512u << 16);
      const uint32_t dX = dK + wg * 512;
      constexpr uint32_t RING = OFF_RING >> 4;
      auto waitA = [&](int n) { mbar_wait(bars + 8 * (B_FA + rslot(n)), rpar(n)); };
      auto freeA = [&](int n) { mbar_arrive_if(elect, bars + 8 * (B_EA + rslot(n))); };
      auto nop = [] {};

      asm volatile("bar.sync 0, 384;" ::: "memory");
#pragma unroll 1
      for (int i = 0; i < 4; i++) {
        const uint64_t dx = d128(dX + i * 2048), df = d128(dK + (OFF_XB >> 4) + (i & 1) * 1024);
        mbar_wait(bars + 8 * (B_FX + 2 * i), 0);
        wg_fence();
        mma_ss64<0, 0, 2>(cX, df, dx, i);
        mma_ss64<0, 0, 1>(cX, df + 2, dx + 2);
        wg_commit(); wg_wait<1>();
        mbar_arrive_if(elect && i, bars + 8 * (B_EA + rslot(i - 1)));
        mma_ss64<0, 0, 1>(cX, df + 4, dx + 4);
        mma_ss64<0, 0, 1>(cX, df + 6, dx + 6);
        if (i == 0 && tid == 0) PROF_EV(1);
        mbar_wait(bars + 8 * (B_FX + 2 * i + 1), 0);
        wg_fence();
#pragma unroll
        for (int k = 0; k < 4; k++) mma_ss64<0, 0, 1>(cX, df + (512 + k * 2), dx + (1024 + k * 2));
        wg_commit();
        waitA(i);
        wg_fence();
        const uint64_t da = d128(dX + i * 1024), db = d128(dN + RING + i * 1024);
        mma_ss128<0, 1, 2>(cA, da, db, i);
        wg_commit(); wg_wait<1>();
        mbar_arrive_if(elect, bars + 8 * (B_FE + i));
#pragma unroll
        for (int k = 1; k < 4; k++) mma_ss128<0, 1, 1>(cA, da + k * 2, db + k * 128);
        wg_commit();
      }
      fence_regs<0, 32>(cX);
#pragma unroll
      for (int e = 0; e < 16; e++) yf[e] = pack_pin(cX[2 * e], cX[2 * e + 1]);
      if (tid == 0) { PROF_EV(2); PROF_CK(42); }
      {
        waitA(4); mbar_wait(bars + 8 * B_E0, 0);
        const uint64_t de = d128(dN + (wg ? RING : OFF_XB >> 4));
        wg_fence();
        mma_rs128<0, 1, 0>(cB, yf[0], yf[1], yf[2], yf[3], de);
        wg_commit();
        wg_wait<1>();
        freeA(3);
#pragma unroll
        for (int k = 1; k < 4; k++) mma_rs128<0, 1, 1>(cB, yf[4 * k], yf[4 * k + 1], yf[4 * k + 2], yf[4 * k + 3], de + k * 128);
        wg_commit();
      }
      bool rel = false;
      auto acquire = [&](int n) {
        rel = elect;
        if (!mbar_try(bars + 8 * (B_FA + rslot(n)), rpar(n))) { wg_wait<0>(); freeA(n - 1); rel = false; waitA(n); }
      };
      auto freeP = [&](int n) { mbar_arrive_if(rel, bars + 8 * (B_EA + rslot(n - 1))); };
      auto ffn_step = [&](auto first, auto split, float (&acc)[64], int n, int kb, auto done, auto work) {
        constexpr int SPLIT = decltype(split)::value;
        acquire(n);
        wg_fence();
        const uint64_t dx = d128(dX + kb * 1024), db = d128(dN + RING + rslot(n) * 1024);
        mma_ss128<0, 1, decltype(first)::value>(acc, dx, db, kb);
#pragma unroll
        for (int k = 1; k < SPLIT; k++) mma_ss128<0, 1, 1>(acc, dx + k * 2, db + k * 128);
        wg_commit();
        work();
        wg_wait<1>();
        freeP(n);
        done();
        if (SPLIT < 4) {
          wg_fence();
#pragma unroll
          for (int k = SPLIT; k < 4; k++) mma_ss128<0, 1, 1>(acc, dx + k * 2, db + k * 128);
          wg_commit();
        }
      };
      {
        const int s0 = 2 * rb + wg, kr = 2 * ((s0 & 1) | ((s0 & 4) >> 1));
        const int m = lane >> 3, r = lane & 7;
        const uint32_t a0 = sb + OFF_XB + wg * 8192 + (((w >> 1) * 8 + (m >> 1)) * 2 + (w & 1)) * 256 + (m & 1) * 128 + ((r ^ (kr + (m & 1))) << 4);
        ffn_step(IC<1>(), IC<4>(), cA, 5, 4, [&] { fence_regs<0, 64>(cB); }, nop);
        asm volatile("bar.sync 5, 256;" ::: "memory");
        auto stage = [&](int i) {
          stsm4t(a0 + i * 1024, pack_bf16(cB[8 * i] - cB[34 + 8 * i], cB[8 * i + 1] - cB[35 + 8 * i]),
                 pack_bf16(cB[32 + 8 * i] + cB[8 * i + 2], cB[33 + 8 * i] + cB[8 * i + 3]),
                 pack_bf16(cB[8 * i + 4] - cB[38 + 8 * i], cB[8 * i + 5] - cB[39 + 8 * i]),
                 pack_bf16(cB[36 + 8 * i] + cB[8 * i + 6], cB[37 + 8 * i] + cB[8 * i + 7]));
          if (j == 0 && w == 0) {
            const uint32_t a1 = r ? sb + OFF_SP + 1024 : sb + OFF_SP + wg * 512 + (m & 1) * 256 + (m >> 1) * 128;
#pragma unroll
            for (int n = 2 * i; n < 2 * i + 2; n++)
              asm volatile("stmatrix.sync.aligned.m8n8.x4.shared.b16 [%0], {%1,%2,%3,%4};" ::"r"(a1 + ((n ^ (kr + (m >> 1)) ^ r) << 4)),
                           "r"(pack_bf16(cB[4 * n], cB[4 * n + 1])), "r"(pack_bf16(cB[4 * n + 2], cB[4 * n + 3])),
                           "r"(pack_bf16(cB[32 + 4 * n], cB[33 + 4 * n])), "r"(pack_bf16(cB[34 + 4 * n], cB[35 + 4 * n])) : "memory");
          }
        };
        auto publish = [&] {
          asm volatile("fence.proxy.async.shared::cta;" ::: "memory");
          __syncwarp();
          mbar_arrive_if(lane == 0, bars + 8 * (B_XS + wg));
          if (tid == 0) PROF_EV(3);
        };
        stage(0);
        ffn_step(IC<1>(), IC<1>(), cA, 6, 5, nop, nop);
        stage(1);
        ffn_step(IC<1>(), IC<1>(), cA, 7, 6, nop, nop);
        stage(2);
        ffn_step(IC<1>(), IC<2>(), cA, 8, 7, [&] { stage(3); }, nop);
        publish();
      }
      float g0 = 0.f, g1 = 0.f;
      uint32_t tag = 0;
      auto glu = [&](auto& acc, int half, int ho, int i0, int i1) {
#pragma unroll
        for (int i = i0; i < i1; i++) {
          const float o = 1.0f - ((i & 1) ? g1 : g0);
          asm volatile("" : "+f"(acc[2 * i]), "+f"(acc[2 * i + 1]), "+f"(acc[half + 2 * i]), "+f"(acc[half + 1 + 2 * i])::"memory");
          h[ho + i] = pack_pin(fmaxf(acc[2 * i], 0.f) * acc[half + 2 * i] * o, fmaxf(acc[2 * i + 1], 0.f) * acc[half + 1 + 2 * i] * o);
        }
      };
      ffn_step(IC<2>(), IC<1>(), cB, 9, zero, nop, nop);
#pragma unroll 1
      for (int kb = 1; kb < 8; kb++)
        ffn_step(IC<1>(), IC<1>(), cB, 9 + kb, kb, nop, [&] {
          if (kb == 4 + wg) {
            mbar_wait(bars + 8 * B_G, 0);
            const uint32_t gb0 = *(const uint32_t*)(smem + OFF_G + (wg * 64 + w * 16 + g) * 4), gb1 = *(const uint32_t*)(smem + OFF_G + (wg * 64 + w * 16 + g + 8) * 4);
            tag = gb0 & 1; g0 = __uint_as_float(gb0 & ~1u); g1 = __uint_as_float(gb1 & ~1u);
            glu(cA, 32, 0, 0, 8);
          } else if (kb == 6 + wg) glu(cA, 32, 0, 8, 16);
        });
      if (tid == 0) { PROF_EV(4); PROF_CK(43); }
      ffn_step(IC<0>(), IC<1>(), cC, 17, 0, nop, nop);
#pragma unroll 1
      for (int kb = 1; kb < 8; kb++)
        ffn_step(IC<1>(), IC<1>(), cC, 17 + kb, kb, nop, [&] {
          if (kb == 1 + wg) glu(cB, 32, 16, 0, 8);
          else if (kb == 3 + wg) glu(cB, 32, 16, 8, 16);
        });
      if (tid == 0) { PROF_EV(5); PROF_CK(44); }
      auto m_step = [&](auto first, int i) {
        acquire(25 + i);
        wg_fence();
        const uint64_t dx = d128(dX + i * 2048), dm = d64(dN + RING + rslot(25 + i) * 1024);
        mma_ss64<0, 1, decltype(first)::value>(ct, dx, dm);
#pragma unroll
        for (int k = 1; k < MSPLIT; k++) mma_ss64<0, 1, 1>(ct, dx + ((k >> 2) * 1024 + (k & 3) * 2), dm + k * 64);
        wg_commit();
        wg_wait<1>();
        mbar_arrive_if(rel && i < 3, bars + 8 * (B_EA + rslot(24 + i)));
        mbar_arrive_if(elect && i, bars + 8 * (B_ET + i - 1));
        wg_fence();
#pragma unroll
        for (int k = MSPLIT; k < 8; k++) mma_ss64<0, 1, 1>(ct, dx + ((k >> 2) * 1024 + (k & 3) * 2), dm + k * 64);
        wg_commit();
      };
      auto freeT = [&](int t) { mbar_arrive_if(elect, bars + 8 * (B_ET + t)); };
      m_step(IC<0>(), 0);
#pragma unroll 1
      for (int i = 1; i < 5; i++) {
        if (i == 1 + wg) glu(cC, 32, 32, 0, 8);
        else if (i == 3 + wg) glu(cC, 32, 32, 8, 16);
        if (i < 4) m_step(IC<1>(), i);
      }
      waitA(29 + wg);
      if (tid == 0) PROF_EV(6);
      if (tid == 128) PROF_EV(27);
      mbar_wait(bars + 8 * (j == 0 ? B_T : B_TL), 0);
      if (tid == 0) { PROF_EV(7); PROF_CK(45); }
      wg_fence();
      {
        const uint64_t dt = d128(dN + (OFF_T >> 4) + wg * 512), de = d128(dK + RING + (1 + wg) * 1024);
        mma_ss64<0, 1, 0>(ci, de, dt);
        mma_ss64<32, 1, 0>(ci, de + 512, dt);
#pragma unroll
        for (int k = 1; k < 4; k++) {
          mma_ss64<0, 1, 1>(ci, de + k * 2, dt + k * 128);
          mma_ss64<32, 1, 1>(ci, de + (512 + k * 2), dt + k * 128);
        }
        wg_commit();
        wg_wait<1>();
        freeT(3);
        fence_regs<0, 32>(ct);
        glu(ct, 16, 48, 0, 8);
      }

      auto twait = [&](uint32_t bar, uint32_t par, int) { mbar_wait(bar, par); };
      auto tr = [] {};
      const int fo = warp * 128 + lane;
      auto fetch = [&](uint4 (&pv)[4], int z) {
        twait(bars + 8 * (z < 4 ? B_Z + 2 * z + wg : B_HP + z - 4), 0, 8 + z);
        const uint8_t* src = smem + (z < 5 ? OFF_Z + z * U : (z - 5) * U) + fo * 16;
#pragma unroll
        for (int i = 0; i < 4; i++) pv[i] = *(const uint4*)(src + i * 512);
      };
      auto check = [&](uint4 (&pv)[4], int z) {
        const uint32_t t0 = (uint32_t)clock();
        while (__any_sync(0xffffffffu, ((pv[0].x ^ tag) | (pv[1].x ^ tag) | (pv[2].x ^ tag) | (pv[3].x ^ tag)) & 1)) {
#pragma unroll
          for (int i = 0; i < 4; i++) pv[i] = ld_x4(ws->part + (size_t)((rb * 8 + j) * 3 + z - 4) * 1024 + fo + i * 32);
          spin_guard(t0);
        }
#pragma unroll
        for (int i = 0; i < 4; i++) pv[i].x &= ~1u;
      };
      const uint32_t peerZ = mapa(sb + OFF_Z + fo * 16, rank ^ 1), peerB = mapa(bars + 8 * (B_Z + wg), rank ^ 1);
      auto tile_mma = [&](auto off, int t, int k0, int k1, int init) {
        constexpr int O = decltype(off)::value;
        const uint64_t db = d128(dN + (t & 3) * (TB >> 4)), dw = db + rank * 256, dm = db + (rank ? 0 : 1536);
#pragma unroll
        for (int k = k0; k < k1; k++) {
          if (k == 0) mma_rs64<O, 1, 2>(ct, h[0], h[1], h[2], h[3], dw, init);
          else if (k < 14) mma_rs64<O, 1, 1>(ct, h[4 * k], h[4 * k + 1], h[4 * k + 2], h[4 * k + 3], k < 12 ? dw + k * 128 : dm + (k - 12) * 128);
          else mma_rs64<O, 1, 1>(ct, yf[4 * k - 56], yf[4 * k - 55], yf[4 * k - 54], yf[4 * k - 53], db + k * 128);
        }
      };
      auto tile = [&](auto off, int t) {
        constexpr int P = 32 - decltype(off)::value;
        const bool grid = t >= 4 && t < 7, pre = t != 1 && t != 5;
        const int zo = grid ? t - 4 : t == 7 ? 3 : t - 1, z = t - 2;
        const int owner = rb * 8 + 2 * ((q4 + zo + 1) & 3) + rank;
        uint4* dst = ws->part + (size_t)(owner * 3 + zo) * 1024 + fo;
        const uint32_t src = sb + (z < 5 ? OFF_Z + z * U : (z - 5) * U) + fo * 16;
        twait(bars + 8 * (B_FT + (t & 3)), t >> 2, t);
        wg_fence();
        tile_mma(off, t, 0, TH, t >= 3 && t != 6);
        wg_commit();
        wg_wait<1>();
        mbar_arrive_if(elect && t < 6, bars + 8 * (B_ET + t - 1));
        if (t == 1) twait(bars + 8 * B_RDY, 0, 15);
        fence_regs<P, 32>(ct);
        uint32_t pk[16];
#pragma unroll
        for (int i = 0; i < 16; i++) pk[i] = pack_bf16(ct[P + 2 * i], ct[P + 2 * i + 1]);
        wg_fence();
#pragma unroll
        for (int i = 0; i < 4; i++) {
          asm volatile(
              "{\n.reg .pred p;\nsetp.ne.b32 p, %7, 0;\n@p st.relaxed.gpu.global.v4.u32 [%0], {%3,%4,%5,%6};\n"
              "@!p st.async.weak.shared::cluster.mbarrier::complete_tx::bytes.v4.b32 [%1], {%3,%4,%5,%6}, [%2];\n}" ::"l"(dst + i * 32),
              "r"(peerZ + zo * U + i * 512), "r"(peerB + 16 * zo), "r"((pk[4 * i] & ~(uint32_t)grid) | (tag & grid)), "r"(pk[4 * i + 1]), "r"(pk[4 * i + 2]),
              "r"(pk[4 * i + 3]), "r"((int)grid) : "memory");
          if (i == 3) hint_add_if(grid && lane == 0, &ws->cntP[32 * owner + zo]);
          tile_mma(off, t, TH + 2 * i, TH + 2 * i + 2, 0);
        }
        wg_commit();
        if (pre) twait(bars + 8 * (z < 4 ? B_Z + 2 * z + wg : B_HP + z - 4), 0, 8 + z);
        wg_fence();
        uint4 pv[4];
#pragma unroll
        for (int i = 0; i < 4; i++) {
          asm volatile("{\n.reg .pred p;\nsetp.ne.b32 p, %5, 0;\n@p ld.shared.v4.u32 {%0,%1,%2,%3}, [%4];\n}"
                       : "=r"(pv[i].x), "=r"(pv[i].y), "=r"(pv[i].z), "=r"(pv[i].w) : "r"(src + i * 512), "r"((int)pre) : "memory");
          tile_mma(off, t, TH + 8 + i, i < 3 ? TH + 9 + i : 18, 0);
        }
        wg_commit();
        if (pre) {
          if (z >= 4) check(pv, z);
#pragma unroll
          for (int i = 0; i < 4; i++) {
            const uint32_t a[4] = {pv[i].x, pv[i].y, pv[i].z, pv[i].w};
#pragma unroll
            for (int e = 0; e < 4; e++) { ct[P + 8 * i + 2 * e] = bf_lo(a[e]); ct[P + 8 * i + 2 * e + 1] = bf_hi(a[e]); }
          }
        }
      };
      asm volatile("barrier.cluster.wait.aligned;" ::: "memory");
      twait(bars + 8 * B_FT, 0, 0);
      wg_fence();
      tile_mma(IC<0>(), 0, 0, 8, zero);
      wg_commit();
      wg_wait<1>();
      if (elect) asm volatile("mbarrier.arrive.shared::cluster.b64 _, [%0];" ::"r"(mapa(bars + 8 * B_RDY, rank ^ 1)) : "memory");
      mbar_arrive_if(elect, bars + 8 * (B_PZ + 1));
      fence_regs<0, 64>(ci);
#pragma unroll
      for (int i = 0; i < 16; i++) {
        const float gg = ((i & 1) ? g1 : g0) * (2.0f / (2048.0f * 512.0f));
        if (i & 2) yf[i] = pack_pin((ci[2 * i] - ci[28 + 2 * i]) * gg, (ci[2 * i + 1] - ci[29 + 2 * i]) * gg);
        else yf[i] = pack_pin((ci[2 * i] + ci[36 + 2 * i]) * gg, (ci[2 * i + 1] + ci[37 + 2 * i]) * gg);
      }
      wg_fence();
      tile_mma(IC<0>(), 0, 8, 18, 0);
      wg_commit();
      if (tid == 0) PROF_EV(8);
      if (tid == 128) PROF_EV(28);
#pragma unroll 1
      for (int t = 1;; t += 2) {
        tile(IC<32>(), t);
        if (t == 7) break;
        tile(IC<0>(), t + 1);
      }
      if (tid == 0) { PROF_EV(9); PROF_CK(46); }
      if (tid == 128) PROF_EV(29);
      {
        float (&sum)[64] = ct;
        uint4 p2[4], p3[4];
        fetch(p3, 3);
        if (tid == 0) PROF_EV(25);
        fetch(p2, 6);
        if (tid == 0) PROF_EV(24);
        check(p2, 6);
#pragma unroll
        for (int i = 0; i < 4; i++) {
          const uint32_t b[4] = {p2[i].x, p2[i].y, p2[i].z, p2[i].w}, c[4] = {p3[i].x, p3[i].y, p3[i].z, p3[i].w};
#pragma unroll
          for (int e = 0; e < 4; e++) {
            sum[8 * i + 2 * e] += bf_lo(c[e]) + bf_lo(b[e]);
            sum[8 * i + 2 * e + 1] += bf_hi(c[e]) + bf_hi(b[e]);
          }
        }
        if (tid == 0) PROF_EV(14);
        wg_wait<0>();
        fence_regs<32, 32>(ct);
#pragma unroll
        for (int i = 0; i < 32; i++) sum[i] += ct[32 + i];
        const uint32_t stg = sb + OFF_T + warp * 2048;
        const int mr = (lane & 7) + ((lane >> 3) & 1) * 8, mc = lane >> 4;
#pragma unroll
        for (int i = 0; i < 4; i++) {
          const uint32_t a = stg + mr * 128 + (((2 * i + mc) ^ (mr & 7)) << 4);
          asm volatile("stmatrix.sync.aligned.m8n8.x4.shared.b16 [%0], {%1,%2,%3,%4};" ::"r"(a), "r"(pack_bf16(sum[8 * i], sum[8 * i + 1])),
                       "r"(pack_bf16(sum[8 * i + 2], sum[8 * i + 3])), "r"(pack_bf16(sum[8 * i + 4], sum[8 * i + 5])),
                       "r"(pack_bf16(sum[8 * i + 6], sum[8 * i + 7])) : "memory");
        }
        asm volatile("fence.proxy.async.shared::cta;" ::: "memory");
        __syncwarp();
        if (elect_one()) {
          asm volatile("cp.async.bulk.tensor.3d.global.shared::cta.bulk_group [%0, {%2, %3, %4}], [%1];" ::"l"(&maps.o), "r"(stg), "r"(64 * j),
                       "r"(16 * w), "r"(2 * rb + wg) : "memory");
          asm volatile("cp.async.bulk.commit_group;\ncp.async.bulk.wait_group.read 0;" ::: "memory");
        }
      }
      if (tid == 0) { PROF_EV(15); PROF_CK(41); }
      if (tid == 128) PROF_EV(30);
    }
  } else if (warp < 12) {
    asm volatile("setmaxnreg.dec.sync.aligned.u32 104;");
    asm volatile("barrier.cluster.arrive.relaxed.aligned;" ::: "memory");
    const int t = tid - 256, w = warp - 8;
    const uint32_t ep = ld_x1(&ws->epoch[blockIdx.x * 8]);
    const uint32_t tag = (ep + 1) & 1;
    auto w_issue = [&](const CUtensorMap* m) {
          if (elect_one()) { mbar_expect_tx(bars + 8 * (B_WR + w), 3072); tma4d(sb + OFF_T + w * 3072, m, bars + 8 * (B_WR + w), 16 * kg, 0, 2 * w, tn); }
          __syncwarp();
    };
    auto gate_rows = [&] {
      const int r = 16 * j + 4 * w + (lane >> 3);
      const uint4* pg = (const uint4*)gate_w + (lane & 7);
      {
        float a = 0.f;
        asm volatile("bar.sync 4, 256;" ::: "memory");
#pragma unroll 1
        for (int hf = 0; hf < 2; hf++) {
          uint4 v[4], u[4];
#pragma unroll
          for (int kb = 0; kb < 4; kb++) v[kb] = __ldg(pg + (4 * hf + kb) * 8);
          mbar_wait(bars + 8 * (B_FE + 1 + 2 * hf), 0);
          if (hf) w_issue(&maps.wr);
#pragma unroll
          for (int kb = 0; kb < 4; kb++) u[kb] = *(const uint4*)(smem + (4 * hf + kb) * U + r * 128 + (((lane ^ r) & 7) << 4));
#pragma unroll
          for (int kb = 0; kb < 4; kb++) {
            a = fmaf(bf_lo(u[kb].x), bf_lo(v[kb].x), a); a = fmaf(bf_hi(u[kb].x), bf_hi(v[kb].x), a);
            a = fmaf(bf_lo(u[kb].y), bf_lo(v[kb].y), a); a = fmaf(bf_hi(u[kb].y), bf_hi(v[kb].y), a);
            a = fmaf(bf_lo(u[kb].z), bf_lo(v[kb].z), a); a = fmaf(bf_hi(u[kb].z), bf_hi(v[kb].z), a);
            a = fmaf(bf_lo(u[kb].w), bf_lo(v[kb].w), a); a = fmaf(bf_hi(u[kb].w), bf_hi(v[kb].w), a);
          }
        }
#pragma unroll
        for (int o = 4; o; o >>= 1) a += __shfl_xor_sync(0xffffffffu, a, o);
        if ((lane & 7) == 0)
          asm volatile("st.relaxed.gpu.global.f32 [%0], %1;" ::"l"(ws->gate + rb * 128 + r), "f"(tagf(__fdividef(1.0f, 1.0f + __expf(-a)), tag)) : "memory");
        if (t == 0) PROF_EV(18);
      }
    };
    {
      const int g = lane >> 2, q = lane & 3;
      uint32_t wf[32];
      if (!helper) {
        gate_rows();
        const uint32_t wa = sb + OFF_T + w * (3072 + 4) + q * 48 + g * 2;
#pragma unroll 1
        for (int ri = 0; ri < 2; ri++) {
          mbar_wait(bars + 8 * (B_WR + w), ri);
#pragma unroll
          for (int n2 = 0; n2 < 32 / WB; n2++) {
            uint32_t v[WB];
#pragma unroll
            for (int i = 0; i < WB; i++) {
              const int e = n2 * WB + i;
              asm volatile("ld.shared.u16 %0, [%1];" : "=r"(v[i]) : "r"(wa + ((e >> 1) & 7) * 192 + (e & 1) * (1536 + 2) + (e >> 4) * 16) : "memory");
            }
#pragma unroll
            for (int i = 0; i < WB; i++) wf[n2 * WB + i] = __byte_perm(wf[n2 * WB + i], v[i], 0x5432);
            if (WSLEEP) { asm volatile("nanosleep.u32 %0;" ::"r"(WSLEEP + (v[WB - 1] >> 16)) : "memory"); }
          }
          __syncwarp();
          if (ri == 0) w_issue(&maps.wi);
        }
        asm volatile("bar.sync 1, 128;" ::: "memory");
        if (t == 0) PROF_EV(11);
      } else {
        asm volatile("bar.sync 4, 256;" ::: "memory");
        hint_wait(&ws->cntW[0], (ep + 1) * 128u);
        const uint32_t t0 = (uint32_t)clock();
#pragma unroll 1
        for (;;) {
          uint32_t bad = 0;
#pragma unroll
          for (int i = 0; i < 32; i++) {
            const float2 v = ld_x2((const float2*)ws->Wh + (i >> 4) * 2048 + 16 * w + g + 8 * (i & 1) + 64 * q + ((i >> 1) & 7) * 256);
            wf[i] = __float_as_uint(v.x); bad |= __float_as_uint(v.y) ^ tag;
          }
          if (!__any_sync(0xffffffffu, bad & 1)) break;
          spin_guard(t0);
        }
        if (t == 0) PROF_EV(11);
      }
      if (w == 0 && elect_one()) { mbar_expect_tx(bars + 8 * B_W, 8192); bulk_load(sb + OFF_D, dtab, 8192, bars + 8 * B_W); }
      mbar_wait(bars + 8 * B_W, 0);
      mbar_wait(bars + 8 * B_HX, 0);
      if (t == 0) PROF_EV(12);
      const uint32_t dd = (sb & 0x3FFFF) >> 4;
      const uint64_t dF = d128((dd + (OFF_D >> 4)) | (512u << 16)), dI = d128((dd + (OFF_D >> 4)) | (1u << 16)), dA = d128((dd + (OFF_XB >> 4)) | (512u << 16));
      float az[32];
      const int zero = blockIdx.x >> 16;
      uint32_t pf[32];
#pragma unroll
      for (int mt = 0; mt < 2; mt++) {
        wg_fence();
        if (mt == 0) mma_ss64<0, 3, 0>(az, dA, dF);
        else mma_ss64<0, 3, 2>(az, dA + 512, dF, zero);
#pragma unroll
        for (int k = 1; k < 4; k++) mma_ss64<0, 3, 1>(az, dA + (mt * 512 + k * 128), dF + k * 128);
        wg_commit();
        wg_wait<0>();
        fence_regs<0, 32>(az);
#pragma unroll
        for (int i = 0; i < 16; i++) {
          const float wr = bf_lo(wf[16 * mt + i]), wi = bf_hi(wf[16 * mt + i]);
          pf[16 * mt + i] = pack_pin(fmaf(az[2 * i], wr, -az[2 * i + 1] * wi), fmaf(az[2 * i], wi, az[2 * i + 1] * wr));
        }
      }
      if (t == 0) PROF_EV(16);
#pragma unroll
      for (int mt = 0; mt < 2; mt++) {
        wg_fence();
        mma_rs64<0, 0, 2>(az, pf[16 * mt], pf[16 * mt + 1], pf[16 * mt + 2], pf[16 * mt + 3], dI, mt ? (int)helper : zero);
#pragma unroll
        for (int k = 1; k < 4; k++) mma_rs64<0, 0, 1>(az, pf[16 * mt + 4 * k], pf[16 * mt + 4 * k + 1], pf[16 * mt + 4 * k + 2], pf[16 * mt + 4 * k + 3], dI + k * 2);
        wg_commit();
        wg_wait<0>();
        fence_regs<0, 32>(az);
        if (!helper) {
          const int m = lane >> 3, r = lane & 7;
          const int sl = 2 * (m >> 1) + ((r >> 1) & 1) + 4 * (r >> 2);
          const uint32_t a0 = sb + OFF_XB + (2 * w + (m & 1)) * 2048 + sl * 64 + (((mt * 2 + (r & 1)) ^ (sl >> 1)) << 4);
#pragma unroll
          for (int i = 0; i < 4; i++)
            stsm4t(a0 + i * 512, pack_bf16(az[8 * i], az[8 * i + 1]), pack_bf16(az[8 * i + 2], az[8 * i + 3]), pack_bf16(az[8 * i + 4], az[8 * i + 5]),
                   pack_bf16(az[8 * i + 6], az[8 * i + 7]));
        }
      }
      if (helper) {
#pragma unroll
        for (int i = 0; i < 16; i++) {
          const int n = i >> 1, s0 = 8 * (n >> 1) + 2 * (n & 1) + (q & 1) + 4 * (q >> 1);
          if ((n & 1) == (int)(blockIdx.x & 1)) st_u2(ws->Ts + s0 * 64 + 16 * w + g + 8 * (i & 1), pack_bf16(az[2 * i], az[2 * i + 1]), tag);
        }
        __syncwarp();
        hint_add_if(lane == 0, &ws->cntH[0]);
        if (t == 0) { ws->epoch[blockIdx.x * 8] = ep + 1; PROF_EV(13); }
      } else {
        asm volatile("fence.proxy.async.shared::cta;" ::: "memory");
        __syncwarp();
        if (elect_one()) {
          if (t == 0) PROF_EV(17);
          if (SPACE) __nanosleep(SPACE * w);
          asm volatile("cp.async.bulk.tensor.3d.global.shared::cta.bulk_group [%0, {%2, %3, %4}], [%1];" ::"l"(&maps.ts), "r"(sb + OFF_XB + w * 4096),
                       "r"(32 * kg), "r"(0), "r"(8 * tn + 2 * w) : "memory");
          bulk_done_signal(&ws->cntT[32 * j]);
          if (t == 96) PROF_EV(13);
        }
        __syncwarp();
        if (j == 0) {
          hint_wait(&ws->cntH[0], (ep + 1) * 8u);
          const uint32_t t0 = (uint32_t)clock();
          float2 v;
          do { v = ld_x2((const float2*)ws->Ts + 2 * rb * 64 + t); spin_guard(t0); } while (__any_sync(0xffffffffu, (__float_as_uint(v.y) ^ tag) & 1));
          mbar_wait(bars + 8 * B_TL, 0);
          const uint32_t u = __float_as_uint(v.x);
          *(uint16_t*)(smem + OFF_T + t * 128 + ((t & 7) << 4)) = (uint16_t)u;
          *(uint16_t*)(smem + OFF_T + t * 128 + (((t & 7) ^ 1) << 4)) = (uint16_t)(u >> 16);
          asm volatile("fence.proxy.async.shared::cta;" ::: "memory");
          __syncwarp();
          mbar_arrive_if(lane == 0, bars + 8 * B_T);
        }
      }
    }
  } else {
    asm volatile("setmaxnreg.dec.sync.aligned.u32 24;");
    auto xf_load = [&](int q) {
      const uint32_t fb = bars + 8 * (B_FX + q);
      mbar_expect_tx(fb, U + 8192);
      tma3d(sb + q * U, &maps.x, fb, 64 * q, 0, 2 * rb);
      if (q >= 4) mbar_wait(bars + 8 * (B_FE + ((q - 4) >> 1)), 0);
      tma2d(sb + OFF_XB + (q & 3) * 8192, &maps.ft, fb, 64 * q, 64 * j);
    };
    if (elect_one()) {
      if (warp == 14) {
#pragma unroll
        for (int i = 0; i < B_FT; i++) mbar_init(bars + 8 * i, 1);
        asm volatile("fence.mbarrier_init.release.cluster;" ::: "memory");
        if (!helper) {
#pragma unroll 1
          for (int n = 0; n < 2; n++) {
            const uint32_t fb = bars + 8 * (B_FA + n);
            xf_load(2 * n); xf_load(2 * n + 1);
            mbar_expect_tx(fb, U);
            tma2d(sb + OFF_RING + n * U, &maps.g64, fb, f_full, 64 * n);
            tma2d(sb + OFF_RING + n * U + 8192, &maps.u64, fb, f_full, 64 * n);
          }
        }
      } else if (warp == 15) {
#pragma unroll
        for (int i = B_FT; i < NBAR; i++) mbar_init(bars + 8 * i, i < B_EA ? 1 : i < B_T ? 2 : 4);
#pragma unroll
        for (int i = 0; i < 8; i++) mbar_expect_tx(bars + 8 * (B_Z + i), U / 2);
        asm volatile("fence.mbarrier_init.release.cluster;" ::: "memory");
        asm volatile("fence.proxy.async.shared::cta;" ::: "memory");
      } else if (warp == 13) {
#pragma unroll
        for (int i = 1; i < 4; i++) asm volatile("prefetch.tensormap [%0];" ::"l"((const char*)&maps + i * 128) : "memory");
      }
    }
    __syncwarp();
    asm volatile("bar.arrive 0, 384;" ::: "memory");
    asm volatile("bar.arrive 4, 256;" ::: "memory");
    __syncwarp();
    asm volatile("barrier.cluster.arrive.relaxed.aligned;" ::: "memory");
    asm volatile("bar.sync 3, 128;" ::: "memory");
    if (warp == 15 && !helper) {
        mbar_wait(bars + 8 * B_FE, 0);
        const uint32_t tag = (ld_x1(&ws->epoch[blockIdx.x * 8]) + 1) & 1;
        const int c = lane >> 4, jj = 16 * blockIdx.x + (lane & 15), jm = (2048 - jj) & 2047;
        const unsigned short* pr = (const unsigned short*)w_r + 256 * c;
        const unsigned short* pi = (const unsigned short*)w_i + 256 * c;
        const float wr = 0.25f * (bf_lo(__ldg(pr + jj * 257)) + bf_lo(__ldg(pr + jm * 257)));
        const float wi = 0.25f * (bf_lo(__ldg(pi + jj * 257)) - bf_lo(__ldg(pi + jm * 257)));
        st_u2(ws->Wh + c * 2048 + jj, c ? pack_bf16(-wi, wr) : pack_bf16(wr, wi), tag);
        __syncwarp();
        hint_add_if(lane == 0, &ws->cntW[0]);
        mbar_wait(bars + 8 * B_XS, 0);
        const uint32_t t0 = (uint32_t)clock();
        uint4 v;
        do { v = ld_x4(ws->gate + rb * 128 + 4 * lane); spin_guard(t0); } while (__any_sync(0xffffffffu, ((v.x ^ tag) | (v.y ^ tag) | (v.z ^ tag) | (v.w ^ tag)) & 1));
        *(uint4*)(smem + OFF_G + lane * 16) = v;
        __syncwarp();
        mbar_arrive_if(lane < 4, bars + 8 * B_G);
      }
    if ((!helper || warp == 15) && elect_one()) {
      if (warp < 14) {
        const int p = warp - 12;
#pragma unroll 1
        for (int i = 4 + p; i < 14; i += 2) asm volatile("prefetch.tensormap [%0];" ::"l"((const char*)&maps + i * 128) : "memory");
#pragma unroll 1
        for (int n = 2; n < 31; n++) {
          const bool table = n == 4 || n >= 29;
          const int q = n < 4 ? n : n - 1;
          const CUtensorMap* m = table ? &maps.e : n >= 25 ? &maps.g32 + p : &maps.g64 + p;
          const int c0 = table ? 0 : n >= 25 ? f_half : f_full + 64 * (q >> 3);
          const int c1 = table ? (2 * rb + ((n & 1) ^ 1)) * 128 + 64 * p : n >= 25 ? 128 * (n - 25) : 64 * (q & 7);
          const uint32_t fb = bars + 8 * (B_FA + (n & 3)), dst = sb + OFF_RING + (n & 3) * U + p * 8192;
          if (n < 4) mbar_wait(bars + 8 * (B_FE + n - 2), 0);
          else mbar_wait(bars + 8 * (B_EA + (n & 3)), ((n >> 2) & 1) ^ 1);
          tma2d(dst, m, fb, c0, c1);
          if (p == 0) mbar_expect_tx(fb, U);
        }
      } else if (warp == 15) {
        const unsigned ep1 = ld_x1(&ws->epoch[blockIdx.x * 8]) + 1;
        flag_wait(&ws->cntX[helper ? 0 : 32 * j], ep1 * 16u);
        PROF_EV(22);
        mbar_expect_tx(bars + 8 * B_HX, U);
        bulk_load(sb + OFF_XB, ws->X + (size_t)(helper ? 128 : kg * 8 + tn) * 8192, U, bars + 8 * B_HX);
        if (!helper) {
          flag_wait(&ws->cntT[32 * j], ep1 * 64u);
          PROF_EV(23);
          mbar_expect_tx(bars + 8 * B_TL, U);
          tma3d(sb + OFF_T, &maps.t, bars + 8 * B_TL, 64 * j, 0, 2 * rb);
#pragma unroll 1
          for (int i = 0; i < 3; i++) {
            flag_wait(&ws->cntP[32 * (rb * 8 + j) + i], ep1 * 8u);
            mbar_wait(bars + 8 * (B_PZ + (i == 0)), 0);
            if (i == 2) PROF_EV(26);
            mbar_expect_tx(bars + 8 * (B_HP + i), U);
            bulk_load(sb + (i ? (i - 1) * U : OFF_T), ws->part + (size_t)((rb * 8 + j) * 3 + i) * 1024, U, bars + 8 * (B_HP + i));
          }
          ws->epoch[blockIdx.x * 8] = ep1;
        }
      } else {
#pragma unroll 1
        for (int q = 4; q < 8; q++) xf_load(q);
        mbar_wait(bars + 8 * (B_FE + 2), 0);
        mbar_expect_tx(bars + 8 * B_E0, U);
        tma2d(sb + OFF_XB, &maps.e, bars + 8 * B_E0, 0, 2 * rb * 128);
        tma2d(sb + OFF_XB + 8192, &maps.e, bars + 8 * B_E0, 0, 2 * rb * 128 + 64);
#pragma unroll 1
        for (int h2 = 0; h2 < 2; h2++) {
          const int s0 = 2 * rb + h2, sg = (s0 & ~6) | ((s0 & 2) << 1) | ((s0 & 4) >> 1);
          mbar_wait(bars + 8 * (B_XS + h2), 0);
#pragma unroll 1
          for (int c = 0; c < 2; c++) {
            asm volatile("cp.async.bulk.tensor.4d.global.shared::cta.bulk_group [%0, {%2, %3, %4, %5}], [%1];" ::"l"(&maps.xs),
                         "r"(sb + OFF_XB + h2 * 8192 + c * 4096), "r"(0), "r"(sg), "r"(0), "r"(16 * j + 8 * c) : "memory");
            if (j == 0)
              asm volatile("cp.async.bulk.global.shared::cta.bulk_group [%0], [%1], 256;" ::"l"(ws->X + 128 * 8192 + c * 4096 + sg * 128),
                           "r"(sb + OFF_SP + h2 * 512 + c * 256) : "memory");
            if (SPACE && h2 + c < 2) __nanosleep(SPACE);
          }
        }
        bulk_done_signal(&ws->cntX[32 * j]);
        PROF_EV(20);
        if (rb < 8) asm volatile("cp.async.bulk.prefetch.tensor.2d.L2.global [%0, {%1, %2}];" ::"l"(&maps.g32 + (rb >> 2)), "r"(f_half), "r"(128 * (rb & 3)) : "memory");
        else asm volatile("cp.async.bulk.prefetch.tensor.2d.L2.global [%0, {%1, %2}];" ::"l"(&maps.d224), "r"(64 * (rb - 8)), "r"(224 * j) : "memory");
#pragma unroll 1
        for (int t = 0; t < 8; t++) {
          const int i = t < 3 ? t + 1 : t < 6 ? t - 2 : 0;
          const int col = 64 * (2 * ((q4 + i) & 3) + ((t < 3 || t == 6) ? 1 - rank : rank));
          const uint32_t fb = bars + 8 * (B_FT + (t & 3)), dst = sb + (t & 3) * TB;
          mbar_wait(bars + 8 * (B_ET + (t == 2 ? 3 : t & 3)), t >> 2);
          mbar_expect_tx(fb, TB);
          tma2d(dst, &maps.d224, fb, col, 224 * j);
          if (t < 2) mbar_wait(bars + 8 * (B_ET + t + 1), 0);
          tma2d(dst + 28672, &maps.ft, fb, col, 64 * j);
        }
      }
    }
  }
}

typedef CUresult (*EncodeFn)(CUtensorMap*, CUtensorMapDataType, cuuint32_t, void*, const cuuint64_t*, const cuuint64_t*, const cuuint32_t*,
                             const cuuint32_t*, CUtensorMapInterleave, CUtensorMapSwizzle, CUtensorMapL2promotion, CUtensorMapFloatOOBfill);

static void encode(EncodeFn f, CUtensorMap* m, const void* base, int rank, const cuuint64_t* dims, const cuuint64_t* strides, const cuuint32_t* box,
                   CUtensorMapSwizzle sw) {
  cuuint32_t es[5] = {1, 1, 1, 1, 1};
  f(m, CU_TENSOR_MAP_DATA_TYPE_BFLOAT16, rank, (void*)base, dims, strides, box, es, CU_TENSOR_MAP_INTERLEAVE_NONE, sw,
    CU_TENSOR_MAP_L2_PROMOTION_L2_128B, CU_TENSOR_MAP_FLOAT_OOB_FILL_NONE);
}

extern "C" void kernel_launch(void* const* d_in, const int* in_sizes, int n_in, void* d_out, int out_size) {
  (void)in_sizes; (void)n_in; (void)out_size;
  const __nv_bfloat16* x = (const __nv_bfloat16*)d_in[0];
  const __nv_bfloat16* w_r = (const __nv_bfloat16*)d_in[1];
  const __nv_bfloat16* w_i = (const __nv_bfloat16*)d_in[2];
  const __nv_bfloat16* Wg = (const __nv_bfloat16*)d_in[4];
  const __nv_bfloat16* Wu = (const __nv_bfloat16*)d_in[5];
  const __nv_bfloat16* Wd = (const __nv_bfloat16*)d_in[6];
  const __nv_bfloat16* gw = (const __nv_bfloat16*)d_in[7];

  void* fp = nullptr; cudaDriverEntryPointQueryResult qr;
  cudaGetDriverEntryPoint("cuTensorMapEncodeTiled", &fp, cudaEnableDefault, &qr);
  EncodeFn enc = (EncodeFn)fp;
  void *pFT, *pET, *pDT, *pW;
  cudaGetSymbolAddress(&pDT, g_DT); cudaGetSymbolAddress(&pW, g_work);
  void *pX = ((Work*)pW)->X, *pT = ((Work*)pW)->T;
  cudaGetSymbolAddress(&pFT, g_FT); cudaGetSymbolAddress(&pET, g_ET);

  Maps mp;
  const CUtensorMapSwizzle S128 = CU_TENSOR_MAP_SWIZZLE_128B, S64 = CU_TENSOR_MAP_SWIZZLE_64B;
  { cuuint64_t d[3] = {512, 64, 32}, s[2] = {32768, 1024}; cuuint32_t b[3] = {64, 64, 2}, b2[3] = {64, 16, 1};
    encode(enc, &mp.x, x, 3, d, s, b, S128); encode(enc, &mp.o, d_out, 3, d, s, b2, S128); }
  { cuuint64_t d[2] = {512, 512}, s[1] = {1024}; cuuint32_t b[2] = {64, 64}; encode(enc, &mp.ft, pFT, 2, d, s, b, S128); }
  { cuuint64_t d[4] = {128, 32, 2, 129}, s[3] = {256, 8192, 16384}; cuuint32_t b[4] = {128, 1, 2, 8}; encode(enc, &mp.xs, pX, 4, d, s, b, CU_TENSOR_MAP_SWIZZLE_NONE); }
  { cuuint64_t d[3] = {512, 32, 64}, s[2] = {65536, 1024}; cuuint32_t b[3] = {32, 32, 2}; encode(enc, &mp.ts, pT, 3, d, s, b, S64); }
  { cuuint64_t d[3] = {512, 64, 32}, s[2] = {1024, 65536}; cuuint32_t b[3] = {64, 64, 2}; encode(enc, &mp.t, pT, 3, d, s, b, S128); }
  { cuuint64_t d[2] = {64, 4096}, s[1] = {128}; cuuint32_t b[2] = {64, 64}; encode(enc, &mp.e, pET, 2, d, s, b, S128); }
  { cuuint64_t d[2] = {1792, 512}, s[1] = {3584}; cuuint32_t b[2] = {64, 64}, b2[2] = {32, 128};
    encode(enc, &mp.g64, Wg, 2, d, s, b, S128); encode(enc, &mp.u64, Wu, 2, d, s, b, S128);
    encode(enc, &mp.g32, Wg, 2, d, s, b2, S64); encode(enc, &mp.u32, Wu, 2, d, s, b2, S64); }
  { cuuint64_t d[2] = {512, 1792}, s[1] = {1024}; cuuint32_t b[2] = {64, 224}; encode(enc, &mp.d224, Wd, 2, d, s, b, S128); }
  { cuuint64_t d[4] = {264, 32, 8, 8}, s[3] = {32896, 512, 4112}; cuuint32_t b[4] = {24, 32, 2, 1};
    encode(enc, &mp.wr, w_r, 4, d, s, b, CU_TENSOR_MAP_SWIZZLE_NONE); encode(enc, &mp.wi, w_i, 4, d, s, b, CU_TENSOR_MAP_SWIZZLE_NONE); }

  cudaFuncSetAttribute(fused_kernel, cudaFuncAttributeMaxDynamicSharedMemorySize, SMEM_BYTES);
  fused_kernel<<<NCTA, 512, SMEM_BYTES>>>((Work*)pW, (const uint16_t*)pDT, w_r, w_i, gw, x, (const uint16_t*)pFT, Wg, Wu, mp);
}
```

```cpp
#include <cuda_runtime.h>
#include <cuda_bf16.h>
#include <cuda.h>
#include <stdint.h>

namespace tbl {
constexpr double PI = 3.14159265358979323846264338327950288;
constexpr double sin_s(double x) { double t = x, s = x; for (int n = 1; n < 12; n++) { t *= -x * x / ((2 * n) * (2 * n + 1)); s += t; } return s; }
constexpr double cos_s(double x) { double t = 1, s = 1; for (int n = 1; n < 12; n++) { t *= -x * x / ((2 * n - 1) * (2 * n)); s += t; } return s; }
constexpr double cos2048(int m) {
  m &= 2047; if (m > 1024) m = 2048 - m;
  bool neg = false; if (m > 512) { m = 1024 - m; neg = true; }
  double v = (m <= 256) ? cos_s(2 * PI * m / 2048) : sin_s(2 * PI * (512 - m) / 2048);
  return neg ? -v : v;
}
constexpr uint16_t to_bf16(double v) {
  if (v == 0) return 0;
  uint16_t s = 0; if (v < 0) { s = 0x8000; v = -v; }
  int e = 0; while (v >= 2) { v /= 2; e++; } while (v < 1) { v *= 2; e--; }
  double m = (v - 1) * 128; int mi = (int)m; double fr = m - mi;
  if (fr > 0.5 || (fr == 0.5 && (mi & 1))) mi++;
  if (mi == 128) { mi = 0; e++; }
  return (uint16_t)(s | ((e + 127) << 7) | mi);
}
struct CosT { uint16_t v[2048]; constexpr CosT() : v() { for (int i = 0; i < 2048; i++) v[i] = to_bf16(cos2048(i)); } };
struct alignas(1024) FT {
  uint16_t v[512 * 512];
  constexpr FT() : v() {
    CosT c;
    for (int r = 0; r < 512; r++) {
      int k = (r >> 4) * 8 + (r & 7), e = (r >> 3) & 1;
      int mul = 4 * k, add = e ? 512 : 0;
      if (k == 0 && e == 1) { mul = 1024; add = 0; }
      for (int d = 0; d < 512; d++) v[r * 512 + d] = c.v[(d * mul + add) & 2047];
    }
  }
};
struct alignas(1024) ET {
  uint16_t v[2048 * 128];
  constexpr ET() : v() {
    CosT c;
    for (int s = 0; s < 2048; s++)
      for (int j = 0; j < 64; j++) {
        const int o = (s & 31) * 8192 + (s >> 5) * 64 + j;
        v[o] = c.v[(s * j) & 2047]; v[o + 4096] = c.v[(s * j + 512) & 2047];
      }
  }
};
struct alignas(1024) DT {
  uint16_t v[64 * 64];
  constexpr DT() : v() {
    CosT c;
    for (int r = 0; r < 64; r++)
      for (int n = 0; n < 64; n++) {
        const int sg = r >> 1, s0 = (sg & ~6) | ((sg & 2) << 1) | ((sg & 4) >> 1), e = r & 1, f = n & 1;
        const int m = 64 * s0 * (n >> 1) + (e == f ? 0 : e ? -512 : 512);
        v[r * 64 + (((n >> 3) ^ (r & 7)) << 3) + (n & 7)] = c.v[m & 2047];
      }
  }
};
}

__device__ constexpr tbl::FT g_FT = tbl::FT();
__device__ constexpr tbl::ET g_ET = tbl::ET();
__device__ constexpr tbl::DT g_DT = tbl::DT();

struct alignas(1024) Work {
  unsigned epoch[132 * 8];
  unsigned cntX[8 * 32], cntT[8 * 32], cntP[128 * 32], cntW[32], cntH[32];
  alignas(16) float gate[16 * 128];
  alignas(16) uint2 Wh[2 * 2048];
  alignas(16) uint2 Ts[32 * 64];
  alignas(1024) uint16_t X[129 * 8192];
  alignas(1024) uint16_t T[32 * 64 * 512];
  alignas(1024) uint4 part[128 * 3 * 1024];
};
__device__ Work g_work;
#define PROF_EV(i) do {} while (0)
#define PROF_CK(i) do {} while (0)

__device__ __forceinline__ uint32_t smem_u32(const void* p) { return (uint32_t)__cvta_generic_to_shared(p); }
__device__ __forceinline__ void mbar_init(uint32_t bar, uint32_t cnt) { asm volatile("mbarrier.init.shared::cta.b64 [%0], %1;" ::"r"(bar), "r"(cnt)); }
__device__ __forceinline__ void mbar_expect_tx(uint32_t bar, uint32_t bytes) { asm volatile("mbarrier.arrive.expect_tx.shared::cta.b64 _, [%0], %1;" ::"r"(bar), "r"(bytes) : "memory"); }
__device__ __forceinline__ void mbar_arrive(uint32_t bar) { asm volatile("mbarrier.arrive.shared::cta.b64 _, [%0];" ::"r"(bar) : "memory"); }
__device__ __forceinline__ bool elect_one() {
  uint32_t p;
  asm volatile("{\n.reg .pred p;\nelect.sync _|p, 0xffffffff;\nselp.u32 %0, 1, 0, p;\n}" : "=r"(p));
  return p;
}
__device__ __forceinline__ void mbar_arrive_if(bool p, uint32_t bar) {
  asm volatile("{\n.reg .pred p;\nsetp.ne.b32 p, %1, 0;\n@p mbarrier.arrive.shared::cta.b64 _, [%0];\n}" ::"r"(bar), "r"((int)p) : "memory");
}
__device__ __forceinline__ void hint_add_if(bool p, unsigned* a) {
  asm volatile("{\n.reg .pred p;\nsetp.ne.b32 p, %1, 0;\n@p red.relaxed.gpu.global.add.u32 [%0], 1;\n}" ::"l"(a), "r"((int)p) : "memory");
}
__device__ __forceinline__ bool mbar_try(uint32_t bar, uint32_t parity) {
  uint32_t ok;
  asm volatile("{\n.reg .pred p;\nmbarrier.test_wait.parity.shared::cta.b64 p, [%1], %2;\nselp.u32 %0, 1, 0, p;\n}" : "=r"(ok) : "r"(bar), "r"(parity) : "memory");
  return ok;
}
__device__ __forceinline__ void mbar_wait(uint32_t bar, uint32_t parity) {
  asm volatile(
      "{\n.reg .pred p;\n.reg .u32 n;\nmov.u32 n, 0;\n"
      "W_LOOP:\nmbarrier.try_wait.parity.shared::cta.b64 p, [%0], %1;\n@p bra W_DONE;\n"
      "add.u32 n, n, 1;\nsetp.lt.u32 p, n, 0x40000;\n@p bra W_LOOP;\ntrap;\nW_DONE:\n}" ::"r"(bar), "r"(parity) : "memory");
}
__device__ __forceinline__ void bulk_load(uint32_t dst, const void* src, uint32_t bytes, uint32_t bar) {
  asm volatile("cp.async.bulk.shared::cluster.global.mbarrier::complete_tx::bytes [%0], [%1], %2, [%3];" ::"r"(dst), "l"(src), "r"(bytes), "r"(bar) : "memory");
}
__device__ __forceinline__ void cp16(uint32_t dst, const void* src) { asm volatile("cp.async.cg.shared.global [%0], [%1], 16;" ::"r"(dst), "l"(src) : "memory"); }
__device__ __forceinline__ void spin_guard(uint32_t t0) { if ((uint32_t)clock() - t0 > (1u << 30)) __trap(); }
__device__ __forceinline__ float tagf(float v, uint32_t tag) { return __uint_as_float((__float_as_uint(v) & ~1u) | tag); }
__device__ __forceinline__ float untag(float v) { return __uint_as_float(__float_as_uint(v) & ~1u); }
__device__ __forceinline__ void st_x2(float2* p, float a, float b) { asm volatile("st.relaxed.gpu.global.v2.f32 [%0], {%1,%2};" ::"l"(p), "f"(a), "f"(b) : "memory"); }
__device__ __forceinline__ float2 ld_x2(const float2* p) { float2 v; asm volatile("ld.relaxed.gpu.global.v2.f32 {%0,%1}, [%2];" : "=f"(v.x), "=f"(v.y) : "l"(p) : "memory"); return v; }
__device__ __forceinline__ void st_u2(uint2* p, uint32_t a, uint32_t b) { asm volatile("st.relaxed.gpu.global.v2.u32 [%0], {%1,%2};" ::"l"(p), "r"(a), "r"(b) : "memory"); }
__device__ __forceinline__ void prefetch2d(const CUtensorMap* m, int c0, int c1) { asm volatile("cp.async.bulk.prefetch.tensor.2d.L2.global [%0, {%1, %2}];" ::"l"(m), "r"(c0), "r"(c1) : "memory"); }
__device__ __forceinline__ void prefetch1d(const void* p, uint32_t bytes) { asm volatile("cp.async.bulk.prefetch.L2.global [%0], %1;" ::"l"(p), "r"(bytes) : "memory"); }
__device__ __forceinline__ uint32_t ld_x1(const void* p) { uint32_t v; asm volatile("ld.relaxed.gpu.global.u32 %0, [%1];" : "=r"(v) : "l"(p) : "memory"); return v; }
__device__ __forceinline__ uint4 ld_x4(const void* p) { uint4 v; asm volatile("ld.relaxed.gpu.global.v4.u32 {%0,%1,%2,%3}, [%4];" : "=r"(v.x), "=r"(v.y), "=r"(v.z), "=r"(v.w) : "l"(p) : "memory"); return v; }
__device__ __forceinline__ void st_x4(void* p, uint32_t a, uint32_t b, uint32_t c, uint32_t d) { asm volatile("st.relaxed.gpu.global.v4.u32 [%0], {%1,%2,%3,%4};" ::"l"(p), "r"(a), "r"(b), "r"(c), "r"(d) : "memory"); }
__device__ __forceinline__ uint32_t mapa(uint32_t a, uint32_t cta) { uint32_t r; asm volatile("mapa.shared::cluster.u32 %0, %1, %2;" : "=r"(r) : "r"(a), "r"(cta)); return r; }
__device__ __forceinline__ void stsm4t(uint32_t a, uint32_t r0, uint32_t r1, uint32_t r2, uint32_t r3) {
  asm volatile("stmatrix.sync.aligned.m8n8.x4.trans.shared.b16 [%0], {%1,%2,%3,%4};" ::"r"(a), "r"(r0), "r"(r1), "r"(r2), "r"(r3) : "memory");
}
__device__ __forceinline__ void hint_add(unsigned* p) { asm volatile("red.relaxed.gpu.global.add.u32 [%0], 1;" ::"l"(p) : "memory"); }
__device__ __forceinline__ void hint_wait(const unsigned* p, unsigned target) {
  const uint32_t t0 = (uint32_t)clock();
  while ((int)(ld_x1(p) - target) < 0) spin_guard(t0);
}
__device__ __forceinline__ void bulk_done_signal(unsigned* p) {
  asm volatile("cp.async.bulk.commit_group;\ncp.async.bulk.wait_group 0;\nfence.proxy.async.global;" ::: "memory");
  hint_add(p);
}
__device__ __forceinline__ void flag_wait(const unsigned* p, unsigned target) {
  hint_wait(p, target);
  asm volatile("fence.proxy.async.global;" ::: "memory");
}
__device__ __forceinline__ void tma2d(uint32_t dst, const CUtensorMap* m, uint32_t bar, int c0, int c1) {
  asm volatile("cp.async.bulk.tensor.2d.shared::cluster.global.mbarrier::complete_tx::bytes [%0], [%1, {%3, %4}], [%2];" ::"r"(dst), "l"(m), "r"(bar), "r"(c0), "r"(c1) : "memory");
}
__device__ __forceinline__ void tma3d(uint32_t dst, const CUtensorMap* m, uint32_t bar, int c0, int c1, int c2) {
  asm volatile("cp.async.bulk.tensor.3d.shared::cluster.global.mbarrier::complete_tx::bytes [%0], [%1, {%3, %4, %5}], [%2];" ::"r"(dst), "l"(m), "r"(bar), "r"(c0), "r"(c1), "r"(c2) : "memory");
}
__device__ __forceinline__ void tma4d(uint32_t dst, const CUtensorMap* m, uint32_t bar, int c0, int c1, int c2, int c3) {
  asm volatile("cp.async.bulk.tensor.4d.shared::cluster.global.mbarrier::complete_tx::bytes [%0], [%1, {%3, %4, %5, %6}], [%2];" ::"r"(dst), "l"(m), "r"(bar), "r"(c0), "r"(c1), "r"(c2), "r"(c3) : "memory");
}
__device__ __forceinline__ void wg_fence() { asm volatile("wgmma.fence.sync.aligned;" ::: "memory"); }
__device__ __forceinline__ void wg_commit() { asm volatile("wgmma.commit_group.sync.aligned;" ::: "memory"); }
template <int N> __device__ __forceinline__ void wg_wait() { asm volatile("wgmma.wait_group.sync.aligned %0;" ::"n"(N) : "memory"); }
template <int O, int N, int NN> __device__ __forceinline__ void fence_regs(float (&d)[NN]) {
#pragma unroll
  for (int i = 0; i < N; i++) asm volatile("" : "+f"(d[O + i])::"memory");
}
__device__ __forceinline__ uint32_t pack_bf16(float lo, float hi) {
  uint32_t r; asm("cvt.rn.bf16x2.f32 %0, %1, %2;" : "=r"(r) : "f"(hi), "f"(lo)); return r;
}
__device__ __forceinline__ uint32_t pack_pin(float lo, float hi) {
  uint32_t r; asm volatile("cvt.rn.bf16x2.f32 %0, %1, %2;" : "=r"(r) : "f"(hi), "f"(lo) : "memory"); return r;
}
__device__ __forceinline__ float bf_lo(uint32_t u) { return __uint_as_float(u << 16); }
__device__ __forceinline__ float bf_hi(uint32_t u) { return __uint_as_float(u & 0xffff0000u); }

__device__ __forceinline__ uint64_t d128(uint32_t lo) { uint64_t d; asm("mov.b64 %0, {%1, 0x40000040};" : "=l"(d) : "r"(lo)); return d; }
__device__ __forceinline__ uint64_t d64(uint32_t lo) { uint64_t d; asm("mov.b64 %0, {%1, 0x80000020};" : "=l"(d) : "r"(lo)); return d; }
template<int O,int TB,int ACC,int NN> __device__ __forceinline__ void mma_ss64(float (&d)[NN], uint64_t da, uint64_t db, int sd = 0){
  if constexpr (ACC == 1) asm volatile("wgmma.mma_async.sync.aligned.m64n64k16.f32.bf16.bf16 {%0,%1,%2,%3,%4,%5,%6,%7,%8,%9,%10,%11,%12,%13,%14,%15,%16,%17,%18,%19,%20,%21,%22,%23,%24,%25,%26,%27,%28,%29,%30,%31}, %32, %33, 1, 1, 1, %35, %34;"
   : "+f"(d[O+0]), "+f"(d[O+1]), "+f"(d[O+2]), "+f"(d[O+3]), "+f"(d[O+4]), "+f"(d[O+5]), "+f"(d[O+6]), "+f"(d[O+7]), "+f"(d[O+8]), "+f"(d[O+9]), "+f"(d[O+10]), "+f"(d[O+11]), "+f"(d[O+12]), "+f"(d[O+13]), "+f"(d[O+14]), "+f"(d[O+15]), "+f"(d[O+16]), "+f"(d[O+17]), "+f"(d[O+18]), "+f"(d[O+19]), "+f"(d[O+20]), "+f"(d[O+21]), "+f"(d[O+22]), "+f"(d[O+23]), "+f"(d[O+24]), "+f"(d[O+25]), "+f"(d[O+26]), "+f"(d[O+27]), "+f"(d[O+28]), "+f"(d[O+29]), "+f"(d[O+30]), "+f"(d[O+31])
   : "l"(da), "l"(db), "n"(TB & 1), "n"(TB >> 1));
  else if constexpr (ACC == 0) asm volatile("wgmma.mma_async.sync.aligned.m64n64k16.f32.bf16.bf16 {%0,%1,%2,%3,%4,%5,%6,%7,%8,%9,%10,%11,%12,%13,%14,%15,%16,%17,%18,%19,%20,%21,%22,%23,%24,%25,%26,%27,%28,%29,%30,%31}, %32, %33, 0, 1, 1, %35, %34;"
   : "=f"(d[O+0]), "=f"(d[O+1]), "=f"(d[O+2]), "=f"(d[O+3]), "=f"(d[O+4]), "=f"(d[O+5]), "=f"(d[O+6]), "=f"(d[O+7]), "=f"(d[O+8]), "=f"(d[O+9]), "=f"(d[O+10]), "=f"(d[O+11]), "=f"(d[O+12]), "=f"(d[O+13]), "=f"(d[O+14]), "=f"(d[O+15]), "=f"(d[O+16]), "=f"(d[O+17]), "=f"(d[O+18]), "=f"(d[O+19]), "=f"(d[O+20]), "=f"(d[O+21]), "=f"(d[O+22]), "=f"(d[O+23]), "=f"(d[O+24]), "=f"(d[O+25]), "=f"(d[O+26]), "=f"(d[O+27]), "=f"(d[O+28]), "=f"(d[O+29]), "=f"(d[O+30]), "=f"(d[O+31])
   : "l"(da), "l"(db), "n"(TB & 1), "n"(TB >> 1));
  else asm volatile("{\n.reg .pred p;\nsetp.ne.b32 p, %36, 0;\nwgmma.mma_async.sync.aligned.m64n64k16.f32.bf16.bf16 {%0,%1,%2,%3,%4,%5,%6,%7,%8,%9,%10,%11,%12,%13,%14,%15,%16,%17,%18,%19,%20,%21,%22,%23,%24,%25,%26,%27,%28,%29,%30,%31}, %32, %33, p, 1, 1, %35, %34;\n}"
   : "+f"(d[O+0]), "+f"(d[O+1]), "+f"(d[O+2]), "+f"(d[O+3]), "+f"(d[O+4]), "+f"(d[O+5]), "+f"(d[O+6]), "+f"(d[O+7]), "+f"(d[O+8]), "+f"(d[O+9]), "+f"(d[O+10]), "+f"(d[O+11]), "+f"(d[O+12]), "+f"(d[O+13]), "+f"(d[O+14]), "+f"(d[O+15]), "+f"(d[O+16]), "+f"(d[O+17]), "+f"(d[O+18]), "+f"(d[O+19]), "+f"(d[O+20]), "+f"(d[O+21]), "+f"(d[O+22]), "+f"(d[O+23]), "+f"(d[O+24]), "+f"(d[O+25]), "+f"(d[O+26]), "+f"(d[O+27]), "+f"(d[O+28]), "+f"(d[O+29]), "+f"(d[O+30]), "+f"(d[O+31])
   : "l"(da), "l"(db), "n"(TB & 1), "n"(TB >> 1), "r"(sd));
}
template<int O,int TB,int ACC,int NN> __device__ __forceinline__ void mma_rs64(float (&d)[NN], uint32_t a0, uint32_t a1, uint32_t a2, uint32_t a3, uint64_t db, int sd = 0){
  if constexpr (ACC == 1) asm volatile("wgmma.mma_async.sync.aligned.m64n64k16.f32.bf16.bf16 {%0,%1,%2,%3,%4,%5,%6,%7,%8,%9,%10,%11,%12,%13,%14,%15,%16,%17,%18,%19,%20,%21,%22,%23,%24,%25,%26,%27,%28,%29,%30,%31}, {%32,%33,%34,%35}, %36, 1, 1, 1, %37;"
   : "+f"(d[O+0]), "+f"(d[O+1]), "+f"(d[O+2]), "+f"(d[O+3]), "+f"(d[O+4]), "+f"(d[O+5]), "+f"(d[O+6]), "+f"(d[O+7]), "+f"(d[O+8]), "+f"(d[O+9]), "+f"(d[O+10]), "+f"(d[O+11]), "+f"(d[O+12]), "+f"(d[O+13]), "+f"(d[O+14]), "+f"(d[O+15]), "+f"(d[O+16]), "+f"(d[O+17]), "+f"(d[O+18]), "+f"(d[O+19]), "+f"(d[O+20]), "+f"(d[O+21]), "+f"(d[O+22]), "+f"(d[O+23]), "+f"(d[O+24]), "+f"(d[O+25]), "+f"(d[O+26]), "+f"(d[O+27]), "+f"(d[O+28]), "+f"(d[O+29]), "+f"(d[O+30]), "+f"(d[O+31])
   : "r"(a0), "r"(a1), "r"(a2), "r"(a3), "l"(db), "n"(TB));
  else if constexpr (ACC == 0) asm volatile("wgmma.mma_async.sync.aligned.m64n64k16.f32.bf16.bf16 {%0,%1,%2,%3,%4,%5,%6,%7,%8,%9,%10,%11,%12,%13,%14,%15,%16,%17,%18,%19,%20,%21,%22,%23,%24,%25,%26,%27,%28,%29,%30,%31}, {%32,%33,%34,%35}, %36, 0, 1, 1, %37;"
   : "=f"(d[O+0]), "=f"(d[O+1]), "=f"(d[O+2]), "=f"(d[O+3]), "=f"(d[O+4]), "=f"(d[O+5]), "=f"(d[O+6]), "=f"(d[O+7]), "=f"(d[O+8]), "=f"(d[O+9]), "=f"(d[O+10]), "=f"(d[O+11]), "=f"(d[O+12]), "=f"(d[O+13]), "=f"(d[O+14]), "=f"(d[O+15]), "=f"(d[O+16]), "=f"(d[O+17]), "=f"(d[O+18]), "=f"(d[O+19]), "=f"(d[O+20]), "=f"(d[O+21]), "=f"(d[O+22]), "=f"(d[O+23]), "=f"(d[O+24]), "=f"(d[O+25]), "=f"(d[O+26]), "=f"(d[O+27]), "=f"(d[O+28]), "=f"(d[O+29]), "=f"(d[O+30]), "=f"(d[O+31])
   : "r"(a0), "r"(a1), "r"(a2), "r"(a3), "l"(db), "n"(TB));
  else asm volatile("{\n.reg .pred p;\nsetp.ne.b32 p, %38, 0;\nwgmma.mma_async.sync.aligned.m64n64k16.f32.bf16.bf16 {%0,%1,%2,%3,%4,%5,%6,%7,%8,%9,%10,%11,%12,%13,%14,%15,%16,%17,%18,%19,%20,%21,%22,%23,%24,%25,%26,%27,%28,%29,%30,%31}, {%32,%33,%34,%35}, %36, p, 1, 1, %37;\n}"
   : "+f"(d[O+0]), "+f"(d[O+1]), "+f"(d[O+2]), "+f"(d[O+3]), "+f"(d[O+4]), "+f"(d[O+5]), "+f"(d[O+6]), "+f"(d[O+7]), "+f"(d[O+8]), "+f"(d[O+9]), "+f"(d[O+10]), "+f"(d[O+11]), "+f"(d[O+12]), "+f"(d[O+13]), "+f"(d[O+14]), "+f"(d[O+15]), "+f"(d[O+16]), "+f"(d[O+17]), "+f"(d[O+18]), "+f"(d[O+19]), "+f"(d[O+20]), "+f"(d[O+21]), "+f"(d[O+22]), "+f"(d[O+23]), "+f"(d[O+24]), "+f"(d[O+25]), "+f"(d[O+26]), "+f"(d[O+27]), "+f"(d[O+28]), "+f"(d[O+29]), "+f"(d[O+30]), "+f"(d[O+31])
   : "r"(a0), "r"(a1), "r"(a2), "r"(a3), "l"(db), "n"(TB), "r"(sd));
}
template<int O,int TB,int ACC,int NN> __device__ __forceinline__ void mma_ss128(float (&d)[NN], uint64_t da, uint64_t db, int sd = 0){
  if constexpr (ACC == 1) asm volatile("wgmma.mma_async.sync.aligned.m64n128k16.f32.bf16.bf16 {%0,%1,%2,%3,%4,%5,%6,%7,%8,%9,%10,%11,%12,%13,%14,%15,%16,%17,%18,%19,%20,%21,%22,%23,%24,%25,%26,%27,%28,%29,%30,%31,%32,%33,%34,%35,%36,%37,%38,%39,%40,%41,%42,%43,%44,%45,%46,%47,%48,%49,%50,%51,%52,%53,%54,%55,%56,%57,%58,%59,%60,%61,%62,%63}, %64, %65, 1, 1, 1, %67, %66;"
   : "+f"(d[O+0]), "+f"(d[O+1]), "+f"(d[O+2]), "+f"(d[O+3]), "+f"(d[O+4]), "+f"(d[O+5]), "+f"(d[O+6]), "+f"(d[O+7]), "+f"(d[O+8]), "+f"(d[O+9]), "+f"(d[O+10]), "+f"(d[O+11]), "+f"(d[O+12]), "+f"(d[O+13]), "+f"(d[O+14]), "+f"(d[O+15]), "+f"(d[O+16]), "+f"(d[O+17]), "+f"(d[O+18]), "+f"(d[O+19]), "+f"(d[O+20]), "+f"(d[O+21]), "+f"(d[O+22]), "+f"(d[O+23]), "+f"(d[O+24]), "+f"(d[O+25]), "+f"(d[O+26]), "+f"(d[O+27]), "+f"(d[O+28]), "+f"(d[O+29]), "+f"(d[O+30]), "+f"(d[O+31]), "+f"(d[O+32]), "+f"(d[O+33]), "+f"(d[O+34]), "+f"(d[O+35]), "+f"(d[O+36]), "+f"(d[O+37]), "+f"(d[O+38]), "+f"(d[O+39]), "+f"(d[O+40]), "+f"(d[O+41]), "+f"(d[O+42]), "+f"(d[O+43]), "+f"(d[O+44]), "+f"(d[O+45]), "+f"(d[O+46]), "+f"(d[O+47]), "+f"(d[O+48]), "+f"(d[O+49]), "+f"(d[O+50]), "+f"(d[O+51]), "+f"(d[O+52]), "+f"(d[O+53]), "+f"(d[O+54]), "+f"(d[O+55]), "+f"(d[O+56]), "+f"(d[O+57]), "+f"(d[O+58]), "+f"(d[O+59]), "+f"(d[O+60]), "+f"(d[O+61]), "+f"(d[O+62]), "+f"(d[O+63])
   : "l"(da), "l"(db), "n"(TB & 1), "n"(TB >> 1));
  else if constexpr (ACC == 0) asm volatile("wgmma.mma_async.sync.aligned.m64n128k16.f32.bf16.bf16 {%0,%1,%2,%3,%4,%5,%6,%7,%8,%9,%10,%11,%12,%13,%14,%15,%16,%17,%18,%19,%20,%21,%22,%23,%24,%25,%26,%27,%28,%29,%30,%31,%32,%33,%34,%35,%36,%37,%38,%39,%40,%41,%42,%43,%44,%45,%46,%47,%48,%49,%50,%51,%52,%53,%54,%55,%56,%57,%58,%59,%60,%61,%62,%63}, %64, %65, 0, 1, 1, %67, %66;"
   : "=f"(d[O+0]), "=f"(d[O+1]), "=f"(d[O+2]), "=f"(d[O+3]), "=f"(d[O+4]), "=f"(d[O+5]), "=f"(d[O+6]), "=f"(d[O+7]), "=f"(d[O+8]), "=f"(d[O+9]), "=f"(d[O+10]), "=f"(d[O+11]), "=f"(d[O+12]), "=f"(d[O+13]), "=f"(d[O+14]), "=f"(d[O+15]), "=f"(d[O+16]), "=f"(d[O+17]), "=f"(d[O+18]), "=f"(d[O+19]), "=f"(d[O+20]), "=f"(d[O+21]), "=f"(d[O+22]), "=f"(d[O+23]), "=f"(d[O+24]), "=f"(d[O+25]), "=f"(d[O+26]), "=f"(d[O+27]), "=f"(d[O+28]), "=f"(d[O+29]), "=f"(d[O+30]), "=f"(d[O+31]), "=f"(d[O+32]), "=f"(d[O+33]), "=f"(d[O+34]), "=f"(d[O+35]), "=f"(d[O+36]), "=f"(d[O+37]), "=f"(d[O+38]), "=f"(d[O+39]), "=f"(d[O+40]), "=f"(d[O+41]), "=f"(d[O+42]), "=f"(d[O+43]), "=f"(d[O+44]), "=f"(d[O+45]), "=f"(d[O+46]), "=f"(d[O+47]), "=f"(d[O+48]), "=f"(d[O+49]), "=f"(d[O+50]), "=f"(d[O+51]), "=f"(d[O+52]), "=f"(d[O+53]), "=f"(d[O+54]), "=f"(d[O+55]), "=f"(d[O+56]), "=f"(d[O+57]), "=f"(d[O+58]), "=f"(d[O+59]), "=f"(d[O+60]), "=f"(d[O+61]), "=f"(d[O+62]), "=f"(d[O+63])
   : "l"(da), "l"(db), "n"(TB & 1), "n"(TB >> 1));
  else asm volatile("{\n.reg .pred p;\nsetp.ne.b32 p, %68, 0;\nwgmma.mma_async.sync.aligned.m64n128k16.f32.bf16.bf16 {%0,%1,%2,%3,%4,%5,%6,%7,%8,%9,%10,%11,%12,%13,%14,%15,%16,%17,%18,%19,%20,%21,%22,%23,%24,%25,%26,%27,%28,%29,%30,%31,%32,%33,%34,%35,%36,%37,%38,%39,%40,%41,%42,%43,%44,%45,%46,%47,%48,%49,%50,%51,%52,%53,%54,%55,%56,%57,%58,%59,%60,%61,%62,%63}, %64, %65, p, 1, 1, %67, %66;\n}"
   : "+f"(d[O+0]), "+f"(d[O+1]), "+f"(d[O+2]), "+f"(d[O+3]), "+f"(d[O+4]), "+f"(d[O+5]), "+f"(d[O+6]), "+f"(d[O+7]), "+f"(d[O+8]), "+f"(d[O+9]), "+f"(d[O+10]), "+f"(d[O+11]), "+f"(d[O+12]), "+f"(d[O+13]), "+f"(d[O+14]), "+f"(d[O+15]), "+f"(d[O+16]), "+f"(d[O+17]), "+f"(d[O+18]), "+f"(d[O+19]), "+f"(d[O+20]), "+f"(d[O+21]), "+f"(d[O+22]), "+f"(d[O+23]), "+f"(d[O+24]), "+f"(d[O+25]), "+f"(d[O+26]), "+f"(d[O+27]), "+f"(d[O+28]), "+f"(d[O+29]), "+f"(d[O+30]), "+f"(d[O+31]), "+f"(d[O+32]), "+f"(d[O+33]), "+f"(d[O+34]), "+f"(d[O+35]), "+f"(d[O+36]), "+f"(d[O+37]), "+f"(d[O+38]), "+f"(d[O+39]), "+f"(d[O+40]), "+f"(d[O+41]), "+f"(d[O+42]), "+f"(d[O+43]), "+f"(d[O+44]), "+f"(d[O+45]), "+f"(d[O+46]), "+f"(d[O+47]), "+f"(d[O+48]), "+f"(d[O+49]), "+f"(d[O+50]), "+f"(d[O+51]), "+f"(d[O+52]), "+f"(d[O+53]), "+f"(d[O+54]), "+f"(d[O+55]), "+f"(d[O+56]), "+f"(d[O+57]), "+f"(d[O+58]), "+f"(d[O+59]), "+f"(d[O+60]), "+f"(d[O+61]), "+f"(d[O+62]), "+f"(d[O+63])
   : "l"(da), "l"(db), "n"(TB & 1), "n"(TB >> 1), "r"(sd));
}
template<int O,int TB,int ACC,int NN> __device__ __forceinline__ void mma_rs128(float (&d)[NN], uint32_t a0, uint32_t a1, uint32_t a2, uint32_t a3, uint64_t db, int sd = 0){
  if constexpr (ACC == 1) asm volatile("wgmma.mma_async.sync.aligned.m64n128k16.f32.bf16.bf16 {%0,%1,%2,%3,%4,%5,%6,%7,%8,%9,%10,%11,%12,%13,%14,%15,%16,%17,%18,%19,%20,%21,%22,%23,%24,%25,%26,%27,%28,%29,%30,%31,%32,%33,%34,%35,%36,%37,%38,%39,%40,%41,%42,%43,%44,%45,%46,%47,%48,%49,%50,%51,%52,%53,%54,%55,%56,%57,%58,%59,%60,%61,%62,%63}, {%64,%65,%66,%67}, %68, 1, 1, 1, %69;"
   : "+f"(d[O+0]), "+f"(d[O+1]), "+f"(d[O+2]), "+f"(d[O+3]), "+f"(d[O+4]), "+f"(d[O+5]), "+f"(d[O+6]), "+f"(d[O+7]), "+f"(d[O+8]), "+f"(d[O+9]), "+f"(d[O+10]), "+f"(d[O+11]), "+f"(d[O+12]), "+f"(d[O+13]), "+f"(d[O+14]), "+f"(d[O+15]), "+f"(d[O+16]), "+f"(d[O+17]), "+f"(d[O+18]), "+f"(d[O+19]), "+f"(d[O+20]), "+f"(d[O+21]), "+f"(d[O+22]), "+f"(d[O+23]), "+f"(d[O+24]), "+f"(d[O+25]), "+f"(d[O+26]), "+f"(d[O+27]), "+f"(d[O+28]), "+f"(d[O+29]), "+f"(d[O+30]), "+f"(d[O+31]), "+f"(d[O+32]), "+f"(d[O+33]), "+f"(d[O+34]), "+f"(d[O+35]), "+f"(d[O+36]), "+f"(d[O+37]), "+f"(d[O+38]), "+f"(d[O+39]), "+f"(d[O+40]), "+f"(d[O+41]), "+f"(d[O+42]), "+f"(d[O+43]), "+f"(d[O+44]), "+f"(d[O+45]), "+f"(d[O+46]), "+f"(d[O+47]), "+f"(d[O+48]), "+f"(d[O+49]), "+f"(d[O+50]), "+f"(d[O+51]), "+f"(d[O+52]), "+f"(d[O+53]), "+f"(d[O+54]), "+f"(d[O+55]), "+f"(d[O+56]), "+f"(d[O+57]), "+f"(d[O+58]), "+f"(d[O+59]), "+f"(d[O+60]), "+f"(d[O+61]), "+f"(d[O+62]), "+f"(d[O+63])
   : "r"(a0), "r"(a1), "r"(a2), "r"(a3), "l"(db), "n"(TB));
  else if constexpr (ACC == 0) asm volatile("wgmma.mma_async.sync.aligned.m64n128k16.f32.bf16.bf16 {%0,%1,%2,%3,%4,%5,%6,%7,%8,%9,%10,%11,%12,%13,%14,%15,%16,%17,%18,%19,%20,%21,%22,%23,%24,%25,%26,%27,%28,%29,%30,%31,%32,%33,%34,%35,%36,%37,%38,%39,%40,%41,%42,%43,%44,%45,%46,%47,%48,%49,%50,%51,%52,%53,%54,%55,%56,%57,%58,%59,%60,%61,%62,%63}, {%64,%65,%66,%67}, %68, 0, 1, 1, %69;"
   : "=f"(d[O+0]), "=f"(d[O+1]), "=f"(d[O+2]), "=f"(d[O+3]), "=f"(d[O+4]), "=f"(d[O+5]), "=f"(d[O+6]), "=f"(d[O+7]), "=f"(d[O+8]), "=f"(d[O+9]), "=f"(d[O+10]), "=f"(d[O+11]), "=f"(d[O+12]), "=f"(d[O+13]), "=f"(d[O+14]), "=f"(d[O+15]), "=f"(d[O+16]), "=f"(d[O+17]), "=f"(d[O+18]), "=f"(d[O+19]), "=f"(d[O+20]), "=f"(d[O+21]), "=f"(d[O+22]), "=f"(d[O+23]), "=f"(d[O+24]), "=f"(d[O+25]), "=f"(d[O+26]), "=f"(d[O+27]), "=f"(d[O+28]), "=f"(d[O+29]), "=f"(d[O+30]), "=f"(d[O+31]), "=f"(d[O+32]), "=f"(d[O+33]), "=f"(d[O+34]), "=f"(d[O+35]), "=f"(d[O+36]), "=f"(d[O+37]), "=f"(d[O+38]), "=f"(d[O+39]), "=f"(d[O+40]), "=f"(d[O+41]), "=f"(d[O+42]), "=f"(d[O+43]), "=f"(d[O+44]), "=f"(d[O+45]), "=f"(d[O+46]), "=f"(d[O+47]), "=f"(d[O+48]), "=f"(d[O+49]), "=f"(d[O+50]), "=f"(d[O+51]), "=f"(d[O+52]), "=f"(d[O+53]), "=f"(d[O+54]), "=f"(d[O+55]), "=f"(d[O+56]), "=f"(d[O+57]), "=f"(d[O+58]), "=f"(d[O+59]), "=f"(d[O+60]), "=f"(d[O+61]), "=f"(d[O+62]), "=f"(d[O+63])
   : "r"(a0), "r"(a1), "r"(a2), "r"(a3), "l"(db), "n"(TB));
  else asm volatile("{\n.reg .pred p;\nsetp.ne.b32 p, %70, 0;\nwgmma.mma_async.sync.aligned.m64n128k16.f32.bf16.bf16 {%0,%1,%2,%3,%4,%5,%6,%7,%8,%9,%10,%11,%12,%13,%14,%15,%16,%17,%18,%19,%20,%21,%22,%23,%24,%25,%26,%27,%28,%29,%30,%31,%32,%33,%34,%35,%36,%37,%38,%39,%40,%41,%42,%43,%44,%45,%46,%47,%48,%49,%50,%51,%52,%53,%54,%55,%56,%57,%58,%59,%60,%61,%62,%63}, {%64,%65,%66,%67}, %68, p, 1, 1, %69;\n}"
   : "+f"(d[O+0]), "+f"(d[O+1]), "+f"(d[O+2]), "+f"(d[O+3]), "+f"(d[O+4]), "+f"(d[O+5]), "+f"(d[O+6]), "+f"(d[O+7]), "+f"(d[O+8]), "+f"(d[O+9]), "+f"(d[O+10]), "+f"(d[O+11]), "+f"(d[O+12]), "+f"(d[O+13]), "+f"(d[O+14]), "+f"(d[O+15]), "+f"(d[O+16]), "+f"(d[O+17]), "+f"(d[O+18]), "+f"(d[O+19]), "+f"(d[O+20]), "+f"(d[O+21]), "+f"(d[O+22]), "+f"(d[O+23]), "+f"(d[O+24]), "+f"(d[O+25]), "+f"(d[O+26]), "+f"(d[O+27]), "+f"(d[O+28]), "+f"(d[O+29]), "+f"(d[O+30]), "+f"(d[O+31]), "+f"(d[O+32]), "+f"(d[O+33]), "+f"(d[O+34]), "+f"(d[O+35]), "+f"(d[O+36]), "+f"(d[O+37]), "+f"(d[O+38]), "+f"(d[O+39]), "+f"(d[O+40]), "+f"(d[O+41]), "+f"(d[O+42]), "+f"(d[O+43]), "+f"(d[O+44]), "+f"(d[O+45]), "+f"(d[O+46]), "+f"(d[O+47]), "+f"(d[O+48]), "+f"(d[O+49]), "+f"(d[O+50]), "+f"(d[O+51]), "+f"(d[O+52]), "+f"(d[O+53]), "+f"(d[O+54]), "+f"(d[O+55]), "+f"(d[O+56]), "+f"(d[O+57]), "+f"(d[O+58]), "+f"(d[O+59]), "+f"(d[O+60]), "+f"(d[O+61]), "+f"(d[O+62]), "+f"(d[O+63])
   : "r"(a0), "r"(a1), "r"(a2), "r"(a3), "l"(db), "n"(TB), "r"(sd));
}

#define NEARLY 0
#define XAHEAD 3
#define HEADN 6
#define WBATCH 1
#define WB 8
#define WSLEEP 20
#define XSPREAD 4
#define NOSEND 0
#define MSPLIT 3
#define PFALL 1
#define L2PF 1
#define STAG 0
#define EPF 2
#define XNB 2
#define FNB 0
#define GNB 0
#define TH 5
#define PF0 4
#define SPACE 40
#define WPF 1
#define WAFTER 7
#define WPACE 0
#define GATE_AT 4
#define TPACE 40
#define PFMODE 0
#define MAPMODE 1
template <int V> struct IC { static constexpr int value = V; };
struct Maps { CUtensorMap x, ft, g64, u64, e, wr, wi, xs, ts, t, g32, u32, d224, o; };

constexpr int NCTA = 130;
constexpr int U = 16384;
constexpr int TB = 36864;
constexpr int OFF_RING = 8 * U, OFF_Z = 9 * U, OFF_XB = 12 * U, OFF_T = 13 * U, OFF_D = OFF_T;
constexpr int OFF_BAR = 14 * U, OFF_SP = OFF_BAR + 512, OFF_G = OFF_SP + 1024 + 128;
constexpr int SMEM_BYTES = OFF_G + 512;
constexpr int B_FX = 0, B_FA = 8, B_FT = 12, B_Z = 16, B_W = 24, B_HX = 25, B_TL = 26, B_HP = 27, B_WR = 30, B_E0 = 34;
constexpr int B_EA = 35, B_ET = 39, B_PZ = 43, B_RDY = 45, B_FE = 46;
constexpr int B_T = 50, B_XS = 51, B_G = 53, NBAR = 54;
__host__ __device__ constexpr int rslot(int n) { return n & 3; }
__host__ __device__ constexpr int rpar(int n) { return (n >> 2) & 1; }

__global__ void __cluster_dims__(2, 1, 1) __launch_bounds__(512, 1)
fused_kernel(Work* __restrict__ ws, const uint16_t* __restrict__ dtab, const __nv_bfloat16* __restrict__ w_r, const __nv_bfloat16* __restrict__ w_i,
             const __nv_bfloat16* __restrict__ gate_w, const __nv_bfloat16* __restrict__ x, const uint16_t* __restrict__ ftab,
             const __nv_bfloat16* __restrict__ Wg, const __nv_bfloat16* __restrict__ Wu, const __grid_constant__ Maps maps) {
  extern __shared__ __align__(1024) uint8_t smem[];
  if (threadIdx.x < 32 && elect_one()) {
#pragma unroll
    for (int i = 0; i < PF0; i++) asm volatile("prefetch.tensormap [%0];" ::"l"((const char*)&maps + i * 128) : "memory");
  }
  const uint32_t sb = smem_u32(smem);
  const uint32_t bars = sb + OFF_BAR;
  const int tid = threadIdx.x, lane = tid & 31;
  const int warp = __shfl_sync(0xffffffffu, tid >> 5, 0);
  const bool helper = blockIdx.x >= 128;
  const int cl = (blockIdx.x >> 1) & 63, rank = blockIdx.x & 1;
  const int q4 = (cl & 1) | ((cl >> 2) & 2), rb = ((cl >> 1) & 3) | ((cl >> 4) << 2);
  const int j = 2 * q4 + rank;
  const int f_full = 448 * q4 + (rank ? 256 : 0);
  const int f_half = 448 * q4 + (rank ? 224 : 192);
  const int kg = 2 * j + (rb >> 3), tn = rb & 7;

  if (tid == 64) { PROF_EV(0); PROF_CK(40); }
  if (warp < 8) {
    if (!helper) {
      if (tid < 16 * XNB) {
        const int r = 16 * j + (tid & 15);
        asm volatile("prefetch.global.L2 [%0];" ::"l"(x + (size_t)(2 * rb + (r >> 6) + 32 * (r & 63)) * 512 + 64 * (tid >> 4)));
      } else if (tid >= 128 && tid < 128 + 4 * FNB) {
        asm volatile("prefetch.global.L2 [%0];" ::"l"(ftab + (64 * j + 4 * rb + (tid & 3)) * 512 + 64 * ((tid - 128) >> 2)));
      } else if (tid >= 192 && tid < 192 + 8 * GNB) {
        asm volatile("prefetch.global.L2 [%0];" ::"l"(((tid & 4) ? Wu : Wg) + (size_t)(64 * ((tid - 192) >> 3) + 4 * rb + (tid & 3)) * 1792 + f_full));
      }
    }
    asm volatile("barrier.cluster.arrive.relaxed.aligned;" ::: "memory");
    asm volatile("setmaxnreg.inc.sync.aligned.u32 192;");
    if (!helper) {
      const int wg = warp >> 2, w = warp & 3, g = lane >> 2;
      const bool elect = (tid & 127) == 0;
      float cX[32], cA[64], cB[64], cC[64], ci[64], ct[64];
      const int zero = blockIdx.x >> 16;
      uint32_t h[56], yf[16];
      const uint32_t d0 = (sb & 0x3FFFF) >> 4;
      const uint32_t dK = d0 | (1u << 16), dN = d0 | (512u << 16);
      const uint32_t dX = dK + wg * 512;
      constexpr uint32_t RING = OFF_RING >> 4;
      auto waitA = [&](int n) { mbar_wait(bars + 8 * (B_FA + rslot(n)), rpar(n)); };
      auto freeA = [&](int n) { mbar_arrive_if(elect, bars + 8 * (B_EA + rslot(n))); };
      auto nop = [] {};

      asm volatile("bar.sync 0, 384;" ::: "memory");
#pragma unroll 1
      for (int i = 0; i < 4; i++) {
        const uint64_t dx = d128(dX + i * 2048), df = d128(dK + (OFF_XB >> 4) + (i & 1) * 1024);
        mbar_wait(bars + 8 * (B_FX + 2 * i), 0);
        wg_fence();
        mma_ss64<0, 0, 2>(cX, df, dx, i);
        mma_ss64<0, 0, 1>(cX, df + 2, dx + 2);
        wg_commit(); wg_wait<1>();
        mbar_arrive_if(elect && i, bars + 8 * (B_EA + rslot(i - 1)));
        mma_ss64<0, 0, 1>(cX, df + 4, dx + 4);
        mma_ss64<0, 0, 1>(cX, df + 6, dx + 6);
        if (i == 0 && tid == 0) PROF_EV(1);
        mbar_wait(bars + 8 * (B_FX + 2 * i + 1), 0);
        wg_fence();
#pragma unroll
        for (int k = 0; k < 4; k++) mma_ss64<0, 0, 1>(cX, df + (512 + k * 2), dx + (1024 + k * 2));
        wg_commit();
        waitA(i);
        wg_fence();
        const uint64_t da = d128(dX + i * 1024), db = d128(dN + RING + i * 1024);
        mma_ss128<0, 1, 2>(cA, da, db, i);
        wg_commit(); wg_wait<1>();
        mbar_arrive_if(elect, bars + 8 * (B_FE + i));
#pragma unroll
        for (int k = 1; k < 4; k++) mma_ss128<0, 1, 1>(cA, da + k * 2, db + k * 128);
        wg_commit();
      }
      fence_regs<0, 32>(cX);
#pragma unroll
      for (int e = 0; e < 16; e++) yf[e] = pack_pin(cX[2 * e], cX[2 * e + 1]);
      if (tid == 0) { PROF_EV(2); PROF_CK(42); }
      {
        waitA(4); mbar_wait(bars + 8 * B_E0, 0);
        const uint64_t de = d128(dN + (wg ? RING : OFF_XB >> 4));
        wg_fence();
        mma_rs128<0, 1, 0>(cB, yf[0], yf[1], yf[2], yf[3], de);
        wg_commit();
        wg_wait<1>();
        freeA(3);
#pragma unroll
        for (int k = 1; k < 4; k++) mma_rs128<0, 1, 1>(cB, yf[4 * k], yf[4 * k + 1], yf[4 * k + 2], yf[4 * k + 3], de + k * 128);
        wg_commit();
      }
      bool rel = false;
      auto acquire = [&](int n) {
        rel = elect;
        if (!mbar_try(bars + 8 * (B_FA + rslot(n)), rpar(n))) { wg_wait<0>(); freeA(n - 1); rel = false; waitA(n); }
      };
      auto freeP = [&](int n) { mbar_arrive_if(rel, bars + 8 * (B_EA + rslot(n - 1))); };
      auto ffn_step = [&](auto first, auto split, float (&acc)[64], int n, int kb, auto done, auto work) {
        constexpr int SPLIT = decltype(split)::value;
        acquire(n);
        wg_fence();
        const uint64_t dx = d128(dX + kb * 1024), db = d128(dN + RING + rslot(n) * 1024);
        mma_ss128<0, 1, decltype(first)::value>(acc, dx, db, kb);
#pragma unroll
        for (int k = 1; k < SPLIT; k++) mma_ss128<0, 1, 1>(acc, dx + k * 2, db + k * 128);
        wg_commit();
        work();
        wg_wait<1>();
        freeP(n);
        done();
        if (SPLIT < 4) {
          wg_fence();
#pragma unroll
          for (int k = SPLIT; k < 4; k++) mma_ss128<0, 1, 1>(acc, dx + k * 2, db + k * 128);
          wg_commit();
        }
      };
      {
        const int s0 = 2 * rb + wg, kr = 2 * ((s0 & 1) | ((s0 & 4) >> 1));
        const int m = lane >> 3, r = lane & 7;
        const uint32_t a0 = sb + OFF_XB + wg * 8192 + (((w >> 1) * 8 + (m >> 1)) * 2 + (w & 1)) * 256 + (m & 1) * 128 + ((r ^ (kr + (m & 1))) << 4);
        ffn_step(IC<1>(), IC<4>(), cA, 5, 4, [&] { fence_regs<0, 64>(cB); }, nop);
        asm volatile("bar.sync 5, 256;" ::: "memory");
        auto stage = [&](int i) {
          stsm4t(a0 + i * 1024, pack_bf16(cB[8 * i] - cB[34 + 8 * i], cB[8 * i + 1] - cB[35 + 8 * i]),
                 pack_bf16(cB[32 + 8 * i] + cB[8 * i + 2], cB[33 + 8 * i] + cB[8 * i + 3]),
                 pack_bf16(cB[8 * i + 4] - cB[38 + 8 * i], cB[8 * i + 5] - cB[39 + 8 * i]),
                 pack_bf16(cB[36 + 8 * i] + cB[8 * i + 6], cB[37 + 8 * i] + cB[8 * i + 7]));
          if (j == 0 && w == 0) {
            const uint32_t a1 = r ? sb + OFF_SP + 1024 : sb + OFF_SP + wg * 512 + (m & 1) * 256 + (m >> 1) * 128;
#pragma unroll
            for (int n = 2 * i; n < 2 * i + 2; n++)
              asm volatile("stmatrix.sync.aligned.m8n8.x4.shared.b16 [%0], {%1,%2,%3,%4};" ::"r"(a1 + ((n ^ (kr + (m >> 1)) ^ r) << 4)),
                           "r"(pack_bf16(cB[4 * n], cB[4 * n + 1])), "r"(pack_bf16(cB[4 * n + 2], cB[4 * n + 3])),
                           "r"(pack_bf16(cB[32 + 4 * n], cB[33 + 4 * n])), "r"(pack_bf16(cB[34 + 4 * n], cB[35 + 4 * n])) : "memory");
          }
        };
        auto publish = [&] {
          asm volatile("fence.proxy.async.shared::cta;" ::: "memory");
          __syncwarp();
          mbar_arrive_if(lane == 0, bars + 8 * (B_XS + wg));
          if (tid == 0) PROF_EV(3);
        };
        stage(0);
        ffn_step(IC<1>(), IC<1>(), cA, 6, 5, nop, nop);
        stage(1);
        ffn_step(IC<1>(), IC<1>(), cA, 7, 6, nop, nop);
        stage(2);
        ffn_step(IC<1>(), IC<2>(), cA, 8, 7, [&] { stage(3); }, nop);
        publish();
      }
      float g0 = 0.f, g1 = 0.f;
      uint32_t tag = 0;
      auto glu = [&](auto& acc, int half, int ho, int i0, int i1) {
#pragma unroll
        for (int i = i0; i < i1; i++) {
          const float o = 1.0f - ((i & 1) ? g1 : g0);
          asm volatile("" : "+f"(acc[2 * i]), "+f"(acc[2 * i + 1]), "+f"(acc[half + 2 * i]), "+f"(acc[half + 1 + 2 * i])::"memory");
          h[ho + i] = pack_pin(fmaxf(acc[2 * i], 0.f) * acc[half + 2 * i] * o, fmaxf(acc[2 * i + 1], 0.f) * acc[half + 1 + 2 * i] * o);
        }
      };
      ffn_step(IC<2>(), IC<1>(), cB, 9, zero, nop, nop);
#pragma unroll 1
      for (int kb = 1; kb < 8; kb++)
        ffn_step(IC<1>(), IC<1>(), cB, 9 + kb, kb, nop, [&] {
          if (kb == 4 + wg) {
            mbar_wait(bars + 8 * B_G, 0);
            const uint32_t gb0 = *(const uint32_t*)(smem + OFF_G + (wg * 64 + w * 16 + g) * 4), gb1 = *(const uint32_t*)(smem + OFF_G + (wg * 64 + w * 16 + g + 8) * 4);
            tag = gb0 & 1; g0 = __uint_as_float(gb0 & ~1u); g1 = __uint_as_float(gb1 & ~1u);
            glu(cA, 32, 0, 0, 8);
          } else if (kb == 6 + wg) glu(cA, 32, 0, 8, 16);
        });
      if (tid == 0) { PROF_EV(4); PROF_CK(43); }
      ffn_step(IC<0>(), IC<1>(), cC, 17, 0, nop, nop);
#pragma unroll 1
      for (int kb = 1; kb < 8; kb++)
        ffn_step(IC<1>(), IC<1>(), cC, 17 + kb, kb, nop, [&] {
          if (kb == 1 + wg) glu(cB, 32, 16, 0, 8);
          else if (kb == 3 + wg) glu(cB, 32, 16, 8, 16);
        });
      if (tid == 0) { PROF_EV(5); PROF_CK(44); }
      auto m_step = [&](auto first, int i) {
        acquire(25 + i);
        wg_fence();
        const uint64_t dx = d128(dX + i * 2048), dm = d64(dN + RING + rslot(25 + i) * 1024);
        mma_ss64<0, 1, decltype(first)::value>(ct, dx, dm);
#pragma unroll
        for (int k = 1; k < MSPLIT; k++) mma_ss64<0, 1, 1>(ct, dx + ((k >> 2) * 1024 + (k & 3) * 2), dm + k * 64);
        wg_commit();
        wg_wait<1>();
        mbar_arrive_if(rel && i < 3, bars + 8 * (B_EA + rslot(24 + i)));
        mbar_arrive_if(elect && i, bars + 8 * (B_ET + i - 1));
        wg_fence();
#pragma unroll
        for (int k = MSPLIT; k < 8; k++) mma_ss64<0, 1, 1>(ct, dx + ((k >> 2) * 1024 + (k & 3) * 2), dm + k * 64);
        wg_commit();
      };
      auto freeT = [&](int t) { mbar_arrive_if(elect, bars + 8 * (B_ET + t)); };
      m_step(IC<0>(), 0);
#pragma unroll 1
      for (int i = 1; i < 5; i++) {
        if (i == 1 + wg) glu(cC, 32, 32, 0, 8);
        else if (i == 3 + wg) glu(cC, 32, 32, 8, 16);
        if (i < 4) m_step(IC<1>(), i);
      }
      waitA(29 + wg);
      if (tid == 0) PROF_EV(6);
      if (tid == 128) PROF_EV(27);
      mbar_wait(bars + 8 * (j == 0 ? B_T : B_TL), 0);
      if (tid == 0) { PROF_EV(7); PROF_CK(45); }
      wg_fence();
      {
        const uint64_t dt = d128(dN + (OFF_T >> 4) + wg * 512), de = d128(dK + RING + (1 + wg) * 1024);
        mma_ss64<0, 1, 0>(ci, de, dt);
        mma_ss64<32, 1, 0>(ci, de + 512, dt);
#pragma unroll
        for (int k = 1; k < 4; k++) {
          mma_ss64<0, 1, 1>(ci, de + k * 2, dt + k * 128);
          mma_ss64<32, 1, 1>(ci, de + (512 + k * 2), dt + k * 128);
        }
        wg_commit();
        wg_wait<1>();
        freeT(3);
        fence_regs<0, 32>(ct);
        glu(ct, 16, 48, 0, 8);
      }

      auto twait = [&](uint32_t bar, uint32_t par, int) { mbar_wait(bar, par); };
      auto tr = [] {};
      const int fo = warp * 128 + lane;
      auto fetch = [&](uint4 (&pv)[4], int z) {
        twait(bars + 8 * (z < 4 ? B_Z + 2 * z + wg : B_HP + z - 4), 0, 8 + z);
        const uint8_t* src = smem + (z < 5 ? OFF_Z + z * U : (z - 5) * U) + fo * 16;
#pragma unroll
        for (int i = 0; i < 4; i++) pv[i] = *(const uint4*)(src + i * 512);
      };
      auto check = [&](uint4 (&pv)[4], int z) {
        const uint32_t t0 = (uint32_t)clock();
        while (__any_sync(0xffffffffu, ((pv[0].x ^ tag) | (pv[1].x ^ tag) | (pv[2].x ^ tag) | (pv[3].x ^ tag)) & 1)) {
#pragma unroll
          for (int i = 0; i < 4; i++) pv[i] = ld_x4(ws->part + (size_t)((rb * 8 + j) * 3 + z - 4) * 1024 + fo + i * 32);
          spin_guard(t0);
        }
#pragma unroll
        for (int i = 0; i < 4; i++) pv[i].x &= ~1u;
      };
      const uint32_t peerZ = mapa(sb + OFF_Z + fo * 16, rank ^ 1), peerB = mapa(bars + 8 * (B_Z + wg), rank ^ 1);
      auto tile_mma = [&](auto off, int t, int k0, int k1, int init) {
        constexpr int O = decltype(off)::value;
        const uint64_t db = d128(dN + (t & 3) * (TB >> 4)), dw = db + rank * 256, dm = db + (rank ? 0 : 1536);
#pragma unroll
        for (int k = k0; k < k1; k++) {
          if (k == 0) mma_rs64<O, 1, 2>(ct, h[0], h[1], h[2], h[3], dw, init);
          else if (k < 14) mma_rs64<O, 1, 1>(ct, h[4 * k], h[4 * k + 1], h[4 * k + 2], h[4 * k + 3], k < 12 ? dw + k * 128 : dm + (k - 12) * 128);
          else mma_rs64<O, 1, 1>(ct, yf[4 * k - 56], yf[4 * k - 55], yf[4 * k - 54], yf[4 * k - 53], db + k * 128);
        }
      };
      auto tile = [&](auto off, int t) {
        constexpr int P = 32 - decltype(off)::value;
        const bool grid = t >= 4 && t < 7, pre = t != 1 && t != 5;
        const int zo = grid ? t - 4 : t == 7 ? 3 : t - 1, z = t - 2;
        const int owner = rb * 8 + 2 * ((q4 + zo + 1) & 3) + rank;
        uint4* dst = ws->part + (size_t)(owner * 3 + zo) * 1024 + fo;
        const uint32_t src = sb + (z < 5 ? OFF_Z + z * U : (z - 5) * U) + fo * 16;
        twait(bars + 8 * (B_FT + (t & 3)), t >> 2, t);
        wg_fence();
        tile_mma(off, t, 0, TH, t >= 3 && t != 6);
        wg_commit();
        wg_wait<1>();
        mbar_arrive_if(elect && t < 6, bars + 8 * (B_ET + t - 1));
        if (t == 1) twait(bars + 8 * B_RDY, 0, 15);
        fence_regs<P, 32>(ct);
        uint32_t pk[16];
#pragma unroll
        for (int i = 0; i < 16; i++) pk[i] = pack_bf16(ct[P + 2 * i], ct[P + 2 * i + 1]);
        wg_fence();
#pragma unroll
        for (int i = 0; i < 4; i++) {
          asm volatile(
              "{\n.reg .pred p;\nsetp.ne.b32 p, %7, 0;\n@p st.relaxed.gpu.global.v4.u32 [%0], {%3,%4,%5,%6};\n"
              "@!p st.async.weak.shared::cluster.mbarrier::complete_tx::bytes.v4.b32 [%1], {%3,%4,%5,%6}, [%2];\n}" ::"l"(dst + i * 32),
              "r"(peerZ + zo * U + i * 512), "r"(peerB + 16 * zo), "r"((pk[4 * i] & ~(uint32_t)grid) | (tag & grid)), "r"(pk[4 * i + 1]), "r"(pk[4 * i + 2]),
              "r"(pk[4 * i + 3]), "r"((int)grid) : "memory");
          if (i == 3) hint_add_if(grid && lane == 0, &ws->cntP[32 * owner + zo]);
          tile_mma(off, t, TH + 2 * i, TH + 2 * i + 2, 0);
        }
        wg_commit();
        if (pre) twait(bars + 8 * (z < 4 ? B_Z + 2 * z + wg : B_HP + z - 4), 0, 8 + z);
        wg_fence();
        uint4 pv[4];
#pragma unroll
        for (int i = 0; i < 4; i++) {
          asm volatile("{\n.reg .pred p;\nsetp.ne.b32 p, %5, 0;\n@p ld.shared.v4.u32 {%0,%1,%2,%3}, [%4];\n}"
                       : "=r"(pv[i].x), "=r"(pv[i].y), "=r"(pv[i].z), "=r"(pv[i].w) : "r"(src + i * 512), "r"((int)pre) : "memory");
          tile_mma(off, t, TH + 8 + i, i < 3 ? TH + 9 + i : 18, 0);
        }
        wg_commit();
        if (pre) {
          if (z >= 4) check(pv, z);
#pragma unroll
          for (int i = 0; i < 4; i++) {
            const uint32_t a[4] = {pv[i].x, pv[i].y, pv[i].z, pv[i].w};
#pragma unroll
            for (int e = 0; e < 4; e++) { ct[P + 8 * i + 2 * e] = bf_lo(a[e]); ct[P + 8 * i + 2 * e + 1] = bf_hi(a[e]); }
          }
        }
      };
      asm volatile("barrier.cluster.wait.aligned;" ::: "memory");
      twait(bars + 8 * B_FT, 0, 0);
      wg_fence();
      tile_mma(IC<0>(), 0, 0, 8, zero);
      wg_commit();
      wg_wait<1>();
      if (elect) asm volatile("mbarrier.arrive.shared::cluster.b64 _, [%0];" ::"r"(mapa(bars + 8 * B_RDY, rank ^ 1)) : "memory");
      mbar_arrive_if(elect, bars + 8 * (B_PZ + 1));
      fence_regs<0, 64>(ci);
#pragma unroll
      for (int i = 0; i < 16; i++) {
        const float gg = ((i & 1) ? g1 : g0) * (2.0f / (2048.0f * 512.0f));
        if (i & 2) yf[i] = pack_pin((ci[2 * i] - ci[28 + 2 * i]) * gg, (ci[2 * i + 1] - ci[29 + 2 * i]) * gg);
        else yf[i] = pack_pin((ci[2 * i] + ci[36 + 2 * i]) * gg, (ci[2 * i + 1] + ci[37 + 2 * i]) * gg);
      }
      wg_fence();
      tile_mma(IC<0>(), 0, 8, 18, 0);
      wg_commit();
      if (tid == 0) PROF_EV(8);
      if (tid == 128) PROF_EV(28);
#pragma unroll 1
      for (int t = 1;; t += 2) {
        tile(IC<32>(), t);
        if (t == 7) break;
        tile(IC<0>(), t + 1);
      }
      if (tid == 0) { PROF_EV(9); PROF_CK(46); }
      if (tid == 128) PROF_EV(29);
      {
        float (&sum)[64] = ct;
        uint4 p2[4], p3[4];
        fetch(p3, 3);
        if (tid == 0) PROF_EV(25);
        fetch(p2, 6);
        if (tid == 0) PROF_EV(24);
        check(p2, 6);
#pragma unroll
        for (int i = 0; i < 4; i++) {
          const uint32_t b[4] = {p2[i].x, p2[i].y, p2[i].z, p2[i].w}, c[4] = {p3[i].x, p3[i].y, p3[i].z, p3[i].w};
#pragma unroll
          for (int e = 0; e < 4; e++) {
            sum[8 * i + 2 * e] += bf_lo(c[e]) + bf_lo(b[e]);
            sum[8 * i + 2 * e + 1] += bf_hi(c[e]) + bf_hi(b[e]);
          }
        }
        if (tid == 0) PROF_EV(14);
        wg_wait<0>();
        fence_regs<32, 32>(ct);
#pragma unroll
        for (int i = 0; i < 32; i++) sum[i] += ct[32 + i];
        const uint32_t stg = sb + OFF_T + warp * 2048;
        const int mr = (lane & 7) + ((lane >> 3) & 1) * 8, mc = lane >> 4;
#pragma unroll
        for (int i = 0; i < 4; i++) {
          const uint32_t a = stg + mr * 128 + (((2 * i + mc) ^ (mr & 7)) << 4);
          asm volatile("stmatrix.sync.aligned.m8n8.x4.shared.b16 [%0], {%1,%2,%3,%4};" ::"r"(a), "r"(pack_bf16(sum[8 * i], sum[8 * i + 1])),
                       "r"(pack_bf16(sum[8 * i + 2], sum[8 * i + 3])), "r"(pack_bf16(sum[8 * i + 4], sum[8 * i + 5])),
                       "r"(pack_bf16(sum[8 * i + 6], sum[8 * i + 7])) : "memory");
        }
        asm volatile("fence.proxy.async.shared::cta;" ::: "memory");
        __syncwarp();
        if (elect_one()) {
          asm volatile("cp.async.bulk.tensor.3d.global.shared::cta.bulk_group [%0, {%2, %3, %4}], [%1];" ::"l"(&maps.o), "r"(stg), "r"(64 * j),
                       "r"(16 * w), "r"(2 * rb + wg) : "memory");
          asm volatile("cp.async.bulk.commit_group;\ncp.async.bulk.wait_group.read 0;" ::: "memory");
        }
      }
      if (tid == 0) { PROF_EV(15); PROF_CK(41); }
      if (tid == 128) PROF_EV(30);
    }
  } else if (warp < 12) {
    asm volatile("setmaxnreg.dec.sync.aligned.u32 104;");
    asm volatile("barrier.cluster.arrive.relaxed.aligned;" ::: "memory");
    const int t = tid - 256, w = warp - 8;
    const uint32_t ep = ld_x1(&ws->epoch[blockIdx.x * 8]);
    const uint32_t tag = (ep + 1) & 1;
    auto w_issue = [&](const CUtensorMap* m) {
          if (elect_one()) { mbar_expect_tx(bars + 8 * (B_WR + w), 3072); tma4d(sb + OFF_T + w * 3072, m, bars + 8 * (B_WR + w), 16 * kg, 0, 2 * w, tn); }
          __syncwarp();
    };
    auto gate_rows = [&] {
      const int r = 16 * j + 4 * w + (lane >> 3);
      const uint4* pg = (const uint4*)gate_w + (lane & 7);
      {
        float a = 0.f;
        asm volatile("bar.sync 4, 256;" ::: "memory");
#pragma unroll 1
        for (int hf = 0; hf < 2; hf++) {
          uint4 v[4], u[4];
#pragma unroll
          for (int kb = 0; kb < 4; kb++) v[kb] = __ldg(pg + (4 * hf + kb) * 8);
          mbar_wait(bars + 8 * (B_FE + 1 + 2 * hf), 0);
          if (hf) w_issue(&maps.wr);
#pragma unroll
          for (int kb = 0; kb < 4; kb++) u[kb] = *(const uint4*)(smem + (4 * hf + kb) * U + r * 128 + (((lane ^ r) & 7) << 4));
#pragma unroll
          for (int kb = 0; kb < 4; kb++) {
            a = fmaf(bf_lo(u[kb].x), bf_lo(v[kb].x), a); a = fmaf(bf_hi(u[kb].x), bf_hi(v[kb].x), a);
            a = fmaf(bf_lo(u[kb].y), bf_lo(v[kb].y), a); a = fmaf(bf_hi(u[kb].y), bf_hi(v[kb].y), a);
            a = fmaf(bf_lo(u[kb].z), bf_lo(v[kb].z), a); a = fmaf(bf_hi(u[kb].z), bf_hi(v[kb].z), a);
            a = fmaf(bf_lo(u[kb].w), bf_lo(v[kb].w), a); a = fmaf(bf_hi(u[kb].w), bf_hi(v[kb].w), a);
          }
        }
#pragma unroll
        for (int o = 4; o; o >>= 1) a += __shfl_xor_sync(0xffffffffu, a, o);
        if ((lane & 7) == 0)
          asm volatile("st.relaxed.gpu.global.f32 [%0], %1;" ::"l"(ws->gate + rb * 128 + r), "f"(tagf(__fdividef(1.0f, 1.0f + __expf(-a)), tag)) : "memory");
        if (t == 0) PROF_EV(18);
      }
    };
    {
      const int g = lane >> 2, q = lane & 3;
      uint32_t wf[32];
      if (!helper) {
        gate_rows();
        const uint32_t wa = sb + OFF_T + w * (3072 + 4) + q * 48 + g * 2;
#pragma unroll 1
        for (int ri = 0; ri < 2; ri++) {
          mbar_wait(bars + 8 * (B_WR + w), ri);
#pragma unroll
          for (int n2 = 0; n2 < 32 / WB; n2++) {
            uint32_t v[WB];
#pragma unroll
            for (int i = 0; i < WB; i++) {
              const int e = n2 * WB + i;
              asm volatile("ld.shared.u16 %0, [%1];" : "=r"(v[i]) : "r"(wa + ((e >> 1) & 7) * 192 + (e & 1) * (1536 + 2) + (e >> 4) * 16) : "memory");
            }
#pragma unroll
            for (int i = 0; i < WB; i++) wf[n2 * WB + i] = __byte_perm(wf[n2 * WB + i], v[i], 0x5432);
            if (WSLEEP) { asm volatile("nanosleep.u32 %0;" ::"r"(WSLEEP + (v[WB - 1] >> 16)) : "memory"); }
          }
          __syncwarp();
          if (ri == 0) w_issue(&maps.wi);
        }
        asm volatile("bar.sync 1, 128;" ::: "memory");
        if (t == 0) PROF_EV(11);
      } else {
        asm volatile("bar.sync 4, 256;" ::: "memory");
        hint_wait(&ws->cntW[0], (ep + 1) * 128u);
        const uint32_t t0 = (uint32_t)clock();
#pragma unroll 1
        for (;;) {
          uint32_t bad = 0;
#pragma unroll
          for (int i = 0; i < 32; i++) {
            const float2 v = ld_x2((const float2*)ws->Wh + (i >> 4) * 2048 + 16 * w + g + 8 * (i & 1) + 64 * q + ((i >> 1) & 7) * 256);
            wf[i] = __float_as_uint(v.x); bad |= __float_as_uint(v.y) ^ tag;
          }
          if (!__any_sync(0xffffffffu, bad & 1)) break;
          spin_guard(t0);
        }
        if (t == 0) PROF_EV(11);
      }
      if (w == 0 && elect_one()) { mbar_expect_tx(bars + 8 * B_W, 8192); bulk_load(sb + OFF_D, dtab, 8192, bars + 8 * B_W); }
      mbar_wait(bars + 8 * B_W, 0);
      mbar_wait(bars + 8 * B_HX, 0);
      if (t == 0) PROF_EV(12);
      const uint32_t dd = (sb & 0x3FFFF) >> 4;
      const uint64_t dF = d128((dd + (OFF_D >> 4)) | (512u << 16)), dI = d128((dd + (OFF_D >> 4)) | (1u << 16)), dA = d128((dd + (OFF_XB >> 4)) | (512u << 16));
      float az[32];
      const int zero = blockIdx.x >> 16;
      uint32_t pf[32];
#pragma unroll
      for (int mt = 0; mt < 2; mt++) {
        wg_fence();
        if (mt == 0) mma_ss64<0, 3, 0>(az, dA, dF);
        else mma_ss64<0, 3, 2>(az, dA + 512, dF, zero);
#pragma unroll
        for (int k = 1; k < 4; k++) mma_ss64<0, 3, 1>(az, dA + (mt * 512 + k * 128), dF + k * 128);
        wg_commit();
        wg_wait<0>();
        fence_regs<0, 32>(az);
#pragma unroll
        for (int i = 0; i < 16; i++) {
          const float wr = bf_lo(wf[16 * mt + i]), wi = bf_hi(wf[16 * mt + i]);
          pf[16 * mt + i] = pack_pin(fmaf(az[2 * i], wr, -az[2 * i + 1] * wi), fmaf(az[2 * i], wi, az[2 * i + 1] * wr));
        }
      }
      if (t == 0) PROF_EV(16);
      {
        const int m = lane >> 3, r = lane & 7;
        const int sl = 2 * (m >> 1) + ((r >> 1) & 1) + 4 * (r >> 2);
        const uint32_t a0 = sb + OFF_XB + (2 * w + (m & 1)) * 2048 + sl * 64;
        uint32_t pk[16];
#pragma unroll
        for (int mt = 0; mt < 3; mt++) {
          if (mt < 2) {
            wg_fence();
            mma_rs64<0, 0, 2>(az, pf[16 * mt], pf[16 * mt + 1], pf[16 * mt + 2], pf[16 * mt + 3], dI, mt ? (int)helper : zero);
#pragma unroll
            for (int k = 1; k < 4; k++) mma_rs64<0, 0, 1>(az, pf[16 * mt + 4 * k], pf[16 * mt + 4 * k + 1], pf[16 * mt + 4 * k + 2], pf[16 * mt + 4 * k + 3], dI + k * 2);
            wg_commit();
          }
          if (mt > 0 && !helper) {
#pragma unroll
            for (int i = 0; i < 4; i++) stsm4t(a0 + ((((mt - 1) * 2 + (r & 1)) ^ (sl >> 1)) << 4) + i * 512, pk[4 * i], pk[4 * i + 1], pk[4 * i + 2], pk[4 * i + 3]);
          }
          if (mt < 2) {
            wg_wait<0>();
            fence_regs<0, 32>(az);
#pragma unroll
            for (int i = 0; i < 16; i++) pk[i] = pack_pin(az[2 * i], az[2 * i + 1]);
          }
        }
      }
      if (helper) {
#pragma unroll
        for (int i = 0; i < 16; i++) {
          const int n = i >> 1, s0 = 8 * (n >> 1) + 2 * (n & 1) + (q & 1) + 4 * (q >> 1);
          if ((n & 1) == (int)(blockIdx.x & 1)) st_u2(ws->Ts + s0 * 64 + 16 * w + g + 8 * (i & 1), pack_bf16(az[2 * i], az[2 * i + 1]), tag);
        }
        __syncwarp();
        hint_add_if(lane == 0, &ws->cntH[0]);
        if (t == 0) { ws->epoch[blockIdx.x * 8] = ep + 1; PROF_EV(13); }
      } else {
        asm volatile("fence.proxy.async.shared::cta;" ::: "memory");
        __syncwarp();
        if (elect_one()) {
          if (t == 0) PROF_EV(17);
          if (SPACE) __nanosleep(SPACE * w);
          asm volatile("cp.async.bulk.tensor.3d.global.shared::cta.bulk_group [%0, {%2, %3, %4}], [%1];" ::"l"(&maps.ts), "r"(sb + OFF_XB + w * 4096),
                       "r"(32 * kg), "r"(0), "r"(8 * tn + 2 * w) : "memory");
          bulk_done_signal(&ws->cntT[32 * j]);
          if (t == 96) PROF_EV(13);
        }
        __syncwarp();
        if (j == 0) {
          hint_wait(&ws->cntH[0], (ep + 1) * 8u);
          const uint32_t t0 = (uint32_t)clock();
          float2 v;
          do { v = ld_x2((const float2*)ws->Ts + 2 * rb * 64 + t); spin_guard(t0); } while (__any_sync(0xffffffffu, (__float_as_uint(v.y) ^ tag) & 1));
          mbar_wait(bars + 8 * B_TL, 0);
          const uint32_t u = __float_as_uint(v.x);
          *(uint16_t*)(smem + OFF_T + t * 128 + ((t & 7) << 4)) = (uint16_t)u;
          *(uint16_t*)(smem + OFF_T + t * 128 + (((t & 7) ^ 1) << 4)) = (uint16_t)(u >> 16);
          asm volatile("fence.proxy.async.shared::cta;" ::: "memory");
          __syncwarp();
          mbar_arrive_if(lane == 0, bars + 8 * B_T);
        }
      }
    }
  } else {
    asm volatile("setmaxnreg.dec.sync.aligned.u32 24;");
    auto xf_load = [&](int q) {
      const uint32_t fb = bars + 8 * (B_FX + q);
      mbar_expect_tx(fb, U + 8192);
      tma3d(sb + q * U, &maps.x, fb, 64 * q, 0, 2 * rb);
      if (q >= 4) mbar_wait(bars + 8 * (B_FE + ((q - 4) >> 1)), 0);
      tma2d(sb + OFF_XB + (q & 3) * 8192, &maps.ft, fb, 64 * q, 64 * j);
    };
    if (elect_one()) {
      if (warp == 14) {
#pragma unroll
        for (int i = 0; i < B_FT; i++) mbar_init(bars + 8 * i, 1);
        asm volatile("fence.mbarrier_init.release.cluster;" ::: "memory");
        if (!helper) {
#pragma unroll 1
          for (int n = 0; n < 2; n++) {
            const uint32_t fb = bars + 8 * (B_FA + n);
            xf_load(2 * n); xf_load(2 * n + 1);
            mbar_expect_tx(fb, U);
            tma2d(sb + OFF_RING + n * U, &maps.g64, fb, f_full, 64 * n);
            tma2d(sb + OFF_RING + n * U + 8192, &maps.u64, fb, f_full, 64 * n);
          }
        }
      } else if (warp == 15) {
#pragma unroll
        for (int i = B_FT; i < NBAR; i++) mbar_init(bars + 8 * i, i < B_EA ? 1 : i < B_T ? 2 : 4);
#pragma unroll
        for (int i = 0; i < 8; i++) mbar_expect_tx(bars + 8 * (B_Z + i), U / 2);
        asm volatile("fence.mbarrier_init.release.cluster;" ::: "memory");
        asm volatile("fence.proxy.async.shared::cta;" ::: "memory");
      } else if (warp == 13 && !PF0) {
#pragma unroll
        for (int i = 1; i < 4; i++) asm volatile("prefetch.tensormap [%0];" ::"l"((const char*)&maps + i * 128) : "memory");
      }
    }
    __syncwarp();
    asm volatile("bar.arrive 0, 384;" ::: "memory");
    asm volatile("bar.arrive 4, 256;" ::: "memory");
    __syncwarp();
    asm volatile("barrier.cluster.arrive.relaxed.aligned;" ::: "memory");
    asm volatile("bar.sync 3, 128;" ::: "memory");
    if (warp == 15 && !helper) {
        mbar_wait(bars + 8 * B_FE, 0);
        const uint32_t tag = (ld_x1(&ws->epoch[blockIdx.x * 8]) + 1) & 1;
        const int c = lane >> 4, jj = 16 * blockIdx.x + (lane & 15), jm = (2048 - jj) & 2047;
        const unsigned short* pr = (const unsigned short*)w_r + 256 * c;
        const unsigned short* pi = (const unsigned short*)w_i + 256 * c;
        const float wr = 0.25f * (bf_lo(__ldg(pr + jj * 257)) + bf_lo(__ldg(pr + jm * 257)));
        const float wi = 0.25f * (bf_lo(__ldg(pi + jj * 257)) - bf_lo(__ldg(pi + jm * 257)));
        st_u2(ws->Wh + c * 2048 + jj, c ? pack_bf16(-wi, wr) : pack_bf16(wr, wi), tag);
        __syncwarp();
        hint_add_if(lane == 0, &ws->cntW[0]);
        mbar_wait(bars + 8 * B_XS, 0);
        const uint32_t t0 = (uint32_t)clock();
        uint4 v;
        do { v = ld_x4(ws->gate + rb * 128 + 4 * lane); spin_guard(t0); } while (__any_sync(0xffffffffu, ((v.x ^ tag) | (v.y ^ tag) | (v.z ^ tag) | (v.w ^ tag)) & 1));
        *(uint4*)(smem + OFF_G + lane * 16) = v;
        __syncwarp();
        mbar_arrive_if(lane < 4, bars + 8 * B_G);
      }
    if ((!helper || warp == 15) && elect_one()) {
      if (warp < 14) {
        const int p = warp - 12;
#pragma unroll 1
        for (int i = 4 + p; i < 14; i += 2) asm volatile("prefetch.tensormap [%0];" ::"l"((const char*)&maps + i * 128) : "memory");
#pragma unroll 1
        for (int n = 2; n < 31; n++) {
          const bool table = n == 4 || n >= 29;
          const int q = n < 4 ? n : n - 1;
          const CUtensorMap* m = table ? &maps.e : n >= 25 ? &maps.g32 + p : &maps.g64 + p;
          const int c0 = table ? 0 : n >= 25 ? f_half : f_full + 64 * (q >> 3);
          const int c1 = table ? (2 * rb + ((n & 1) ^ 1)) * 128 + 64 * p : n >= 25 ? 128 * (n - 25) : 64 * (q & 7);
          const uint32_t fb = bars + 8 * (B_FA + (n & 3)), dst = sb + OFF_RING + (n & 3) * U + p * 8192;
          if (n < 4) mbar_wait(bars + 8 * (B_FE + n - 2), 0);
          else mbar_wait(bars + 8 * (B_EA + (n & 3)), ((n >> 2) & 1) ^ 1);
          tma2d(dst, m, fb, c0, c1);
          if (p == 0) mbar_expect_tx(fb, U);
        }
      } else if (warp == 15) {
        const unsigned ep1 = ld_x1(&ws->epoch[blockIdx.x * 8]) + 1;
        flag_wait(&ws->cntX[helper ? 0 : 32 * j], ep1 * 16u);
        PROF_EV(22);
        mbar_expect_tx(bars + 8 * B_HX, U);
        bulk_load(sb + OFF_XB, ws->X + (size_t)(helper ? 128 : kg * 8 + tn) * 8192, U, bars + 8 * B_HX);
        if (!helper) {
          flag_wait(&ws->cntT[32 * j], ep1 * 64u);
          PROF_EV(23);
          mbar_expect_tx(bars + 8 * B_TL, U);
          tma3d(sb + OFF_T, &maps.t, bars + 8 * B_TL, 64 * j, 0, 2 * rb);
#pragma unroll 1
          for (int i = 0; i < 3; i++) {
            flag_wait(&ws->cntP[32 * (rb * 8 + j) + i], ep1 * 8u);
            mbar_wait(bars + 8 * (B_PZ + (i == 0)), 0);
            if (i == 2) PROF_EV(26);
            mbar_expect_tx(bars + 8 * (B_HP + i), U);
            bulk_load(sb + (i ? (i - 1) * U : OFF_T), ws->part + (size_t)((rb * 8 + j) * 3 + i) * 1024, U, bars + 8 * (B_HP + i));
          }
          ws->epoch[blockIdx.x * 8] = ep1;
        }
      } else {
#pragma unroll 1
        for (int q = 4; q < 8; q++) xf_load(q);
        mbar_wait(bars + 8 * (B_FE + 2), 0);
        mbar_expect_tx(bars + 8 * B_E0, U);
        tma2d(sb + OFF_XB, &maps.e, bars + 8 * B_E0, 0, 2 * rb * 128);
        tma2d(sb + OFF_XB + 8192, &maps.e, bars + 8 * B_E0, 0, 2 * rb * 128 + 64);
#pragma unroll 1
        for (int h2 = 0; h2 < 2; h2++) {
          const int s0 = 2 * rb + h2, sg = (s0 & ~6) | ((s0 & 2) << 1) | ((s0 & 4) >> 1);
          mbar_wait(bars + 8 * (B_XS + h2), 0);
#pragma unroll 1
          for (int c = 0; c < 2; c++) {
            asm volatile("cp.async.bulk.tensor.4d.global.shared::cta.bulk_group [%0, {%2, %3, %4, %5}], [%1];" ::"l"(&maps.xs),
                         "r"(sb + OFF_XB + h2 * 8192 + c * 4096), "r"(0), "r"(sg), "r"(0), "r"(16 * j + 8 * c) : "memory");
            if (j == 0)
              asm volatile("cp.async.bulk.global.shared::cta.bulk_group [%0], [%1], 256;" ::"l"(ws->X + 128 * 8192 + c * 4096 + sg * 128),
                           "r"(sb + OFF_SP + h2 * 512 + c * 256) : "memory");
            if (SPACE && h2 + c < 2) __nanosleep(SPACE);
          }
        }
        bulk_done_signal(&ws->cntX[32 * j]);
        PROF_EV(20);
        if (rb < 8) asm volatile("cp.async.bulk.prefetch.tensor.2d.L2.global [%0, {%1, %2}];" ::"l"(&maps.g32 + (rb >> 2)), "r"(f_half), "r"(128 * (rb & 3)) : "memory");
        else asm volatile("cp.async.bulk.prefetch.tensor.2d.L2.global [%0, {%1, %2}];" ::"l"(&maps.d224), "r"(64 * (rb - 8)), "r"(224 * j) : "memory");
#pragma unroll 1
        for (int t = 0; t < 8; t++) {
          const int i = t < 3 ? t + 1 : t < 6 ? t - 2 : 0;
          const int col = 64 * (2 * ((q4 + i) & 3) + ((t < 3 || t == 6) ? 1 - rank : rank));
          const uint32_t fb = bars + 8 * (B_FT + (t & 3)), dst = sb + (t & 3) * TB;
          mbar_wait(bars + 8 * (B_ET + (t == 2 ? 3 : t & 3)), t >> 2);
          mbar_expect_tx(fb, TB);
          tma2d(dst, &maps.d224, fb, col, 224 * j);
          if (t < 2) mbar_wait(bars + 8 * (B_ET + t + 1), 0);
          tma2d(dst + 28672, &maps.ft, fb, col, 64 * j);
        }
      }
    }
  }
}

typedef CUresult (*EncodeFn)(CUtensorMap*, CUtensorMapDataType, cuuint32_t, void*, const cuuint64_t*, const cuuint64_t*, const cuuint32_t*,
                             const cuuint32_t*, CUtensorMapInterleave, CUtensorMapSwizzle, CUtensorMapL2promotion, CUtensorMapFloatOOBfill);

static void encode(EncodeFn f, CUtensorMap* m, const void* base, int rank, const cuuint64_t* dims, const cuuint64_t* strides, const cuuint32_t* box,
                   CUtensorMapSwizzle sw) {
  cuuint32_t es[5] = {1, 1, 1, 1, 1};
  f(m, CU_TENSOR_MAP_DATA_TYPE_BFLOAT16, rank, (void*)base, dims, strides, box, es, CU_TENSOR_MAP_INTERLEAVE_NONE, sw,
    CU_TENSOR_MAP_L2_PROMOTION_L2_128B, CU_TENSOR_MAP_FLOAT_OOB_FILL_NONE);
}

extern "C" void kernel_launch(void* const* d_in, const int* in_sizes, int n_in, void* d_out, int out_size) {
  (void)in_sizes; (void)n_in; (void)out_size;
  const __nv_bfloat16* x = (const __nv_bfloat16*)d_in[0];
  const __nv_bfloat16* w_r = (const __nv_bfloat16*)d_in[1];
  const __nv_bfloat16* w_i = (const __nv_bfloat16*)d_in[2];
  const __nv_bfloat16* Wg = (const __nv_bfloat16*)d_in[4];
  const __nv_bfloat16* Wu = (const __nv_bfloat16*)d_in[5];
  const __nv_bfloat16* Wd = (const __nv_bfloat16*)d_in[6];
  const __nv_bfloat16* gw = (const __nv_bfloat16*)d_in[7];

  void* fp = nullptr; cudaDriverEntryPointQueryResult qr;
  cudaGetDriverEntryPoint("cuTensorMapEncodeTiled", &fp, cudaEnableDefault, &qr);
  EncodeFn enc = (EncodeFn)fp;
  void *pFT, *pET, *pDT, *pW;
  cudaGetSymbolAddress(&pDT, g_DT); cudaGetSymbolAddress(&pW, g_work);
  void *pX = ((Work*)pW)->X, *pT = ((Work*)pW)->T;
  cudaGetSymbolAddress(&pFT, g_FT); cudaGetSymbolAddress(&pET, g_ET);

  Maps mp;
  const CUtensorMapSwizzle S128 = CU_TENSOR_MAP_SWIZZLE_128B, S64 = CU_TENSOR_MAP_SWIZZLE_64B;
  { cuuint64_t d[3] = {512, 64, 32}, s[2] = {32768, 1024}; cuuint32_t b[3] = {64, 64, 2}, b2[3] = {64, 16, 1};
    encode(enc, &mp.x, x, 3, d, s, b, S128); encode(enc, &mp.o, d_out, 3, d, s, b2, S128); }
  { cuuint64_t d[2] = {512, 512}, s[1] = {1024}; cuuint32_t b[2] = {64, 64}; encode(enc, &mp.ft, pFT, 2, d, s, b, S128); }
  { cuuint64_t d[4] = {128, 32, 2, 129}, s[3] = {256, 8192, 16384}; cuuint32_t b[4] = {128, 1, 2, 8}; encode(enc, &mp.xs, pX, 4, d, s, b, CU_TENSOR_MAP_SWIZZLE_NONE); }
  { cuuint64_t d[3] = {512, 32, 64}, s[2] = {65536, 1024}; cuuint32_t b[3] = {32, 32, 2}; encode(enc, &mp.ts, pT, 3, d, s, b, S64); }
  { cuuint64_t d[3] = {512, 64, 32}, s[2] = {1024, 65536}; cuuint32_t b[3] = {64, 64, 2}; encode(enc, &mp.t, pT, 3, d, s, b, S128); }
  { cuuint64_t d[2] = {64, 4096}, s[1] = {128}; cuuint32_t b[2] = {64, 64}; encode(enc, &mp.e, pET, 2, d, s, b, S128); }
  { cuuint64_t d[2] = {1792, 512}, s[1] = {3584}; cuuint32_t b[2] = {64, 64}, b2[2] = {32, 128};
    encode(enc, &mp.g64, Wg, 2, d, s, b, S128); encode(enc, &mp.u64, Wu, 2, d, s, b, S128);
    encode(enc, &mp.g32, Wg, 2, d, s, b2, S64); encode(enc, &mp.u32, Wu, 2, d, s, b2, S64); }
  { cuuint64_t d[2] = {512, 1792}, s[1] = {1024}; cuuint32_t b[2] = {64, 224}; encode(enc, &mp.d224, Wd, 2, d, s, b, S128); }
  { cuuint64_t d[4] = {264, 32, 8, 8}, s[3] = {32896, 512, 4112}; cuuint32_t b[4] = {24, 32, 2, 1};
    encode(enc, &mp.wr, w_r, 4, d, s, b, CU_TENSOR_MAP_SWIZZLE_NONE); encode(enc, &mp.wi, w_i, 4, d, s, b, CU_TENSOR_MAP_SWIZZLE_NONE); }

  cudaFuncSetAttribute(fused_kernel, cudaFuncAttributeMaxDynamicSharedMemorySize, SMEM_BYTES);
  fused_kernel<<<NCTA, 512, SMEM_BYTES>>>((Work*)pW, (const uint16_t*)pDT, w_r, w_i, gw, x, (const uint16_t*)pFT, Wg, Wu, mp);
}
```

```cpp
#include <cuda_runtime.h>
#include <cuda_bf16.h>
#include <cuda.h>
#include <stdint.h>

namespace tbl {
constexpr double PI = 3.14159265358979323846264338327950288;
constexpr double sin_s(double x) { double t = x, s = x; for (int n = 1; n < 12; n++) { t *= -x * x / ((2 * n) * (2 * n + 1)); s += t; } return s; }
constexpr double cos_s(double x) { double t = 1, s = 1; for (int n = 1; n < 12; n++) { t *= -x * x / ((2 * n - 1) * (2 * n)); s += t; } return s; }
constexpr double cos2048(int m) {
  m &= 2047; if (m > 1024) m = 2048 - m;
  bool neg = false; if (m > 512) { m = 1024 - m; neg = true; }
  double v = (m <= 256) ? cos_s(2 * PI * m / 2048) : sin_s(2 * PI * (512 - m) / 2048);
  return neg ? -v : v;
}
constexpr uint16_t to_bf16(double v) {
  if (v == 0) return 0;
  uint16_t s = 0; if (v < 0) { s = 0x8000; v = -v; }
  int e = 0; while (v >= 2) { v /= 2; e++; } while (v < 1) { v *= 2; e--; }
  double m = (v - 1) * 128; int mi = (int)m; double fr = m - mi;
  if (fr > 0.5 || (fr == 0.5 && (mi & 1))) mi++;
  if (mi == 128) { mi = 0; e++; }
  return (uint16_t)(s | ((e + 127) << 7) | mi);
}
struct CosT { uint16_t v[2048]; constexpr CosT() : v() { for (int i = 0; i < 2048; i++) v[i] = to_bf16(cos2048(i)); } };
struct alignas(1024) FT {
  uint16_t v[512 * 512];
  constexpr FT() : v() {
    CosT c;
    for (int r = 0; r < 512; r++) {
      int k = (r >> 4) * 8 + (r & 7), e = (r >> 3) & 1;
      int mul = 4 * k, add = e ? 512 : 0;
      if (k == 0 && e == 1) { mul = 1024; add = 0; }
      for (int d = 0; d < 512; d++) v[r * 512 + d] = c.v[(d * mul + add) & 2047];
    }
  }
};
struct alignas(1024) ET {
  uint16_t v[2048 * 128];
  constexpr ET() : v() {
    CosT c;
    for (int s = 0; s < 2048; s++)
      for (int j = 0; j < 64; j++) {
        const int o = (s & 31) * 8192 + (s >> 5) * 64 + j;
        v[o] = c.v[(s * j) & 2047]; v[o + 4096] = c.v[(s * j + 512) & 2047];
      }
  }
};
struct alignas(1024) DT {
  uint16_t v[64 * 64];
  constexpr DT() : v() {
    CosT c;
    for (int r = 0; r < 64; r++)
      for (int n = 0; n < 64; n++) {
        const int sg = r >> 1, s0 = (sg & ~6) | ((sg & 2) << 1) | ((sg & 4) >> 1), e = r & 1, f = n & 1;
        const int m = 64 * s0 * (n >> 1) + (e == f ? 0 : e ? -512 : 512);
        v[r * 64 + (((n >> 3) ^ (r & 7)) << 3) + (n & 7)] = c.v[m & 2047];
      }
  }
};
}

__device__ constexpr tbl::FT g_FT = tbl::FT();
__device__ constexpr tbl::ET g_ET = tbl::ET();
__device__ constexpr tbl::DT g_DT = tbl::DT();

struct alignas(1024) Work {
  unsigned epoch[132 * 8];
  unsigned cntX[8 * 32], cntT[8 * 32], cntP[128 * 32], cntW[32], cntH[32];
  alignas(16) float gate[16 * 128];
  alignas(16) uint2 Wh[2 * 2048];
  alignas(16) uint2 Ts[32 * 64];
  alignas(1024) uint16_t X[129 * 8192];
  alignas(1024) uint16_t T[32 * 64 * 512];
  alignas(1024) uint4 part[128 * 3 * 1024];
};
__device__ Work g_work;
#define PROF_EV(i) do {} while (0)
#define PROF_CK(i) do {} while (0)

__device__ __forceinline__ uint32_t smem_u32(const void* p) { return (uint32_t)__cvta_generic_to_shared(p); }
__device__ __forceinline__ void mbar_init(uint32_t bar, uint32_t cnt) { asm volatile("mbarrier.init.shared::cta.b64 [%0], %1;" ::"r"(bar), "r"(cnt)); }
__device__ __forceinline__ void mbar_expect_tx(uint32_t bar, uint32_t bytes) { asm volatile("mbarrier.arrive.expect_tx.shared::cta.b64 _, [%0], %1;" ::"r"(bar), "r"(bytes) : "memory"); }
__device__ __forceinline__ void mbar_arrive(uint32_t bar) { asm volatile("mbarrier.arrive.shared::cta.b64 _, [%0];" ::"r"(bar) : "memory"); }
__device__ __forceinline__ bool elect_one() {
  uint32_t p;
  asm volatile("{\n.reg .pred p;\nelect.sync _|p, 0xffffffff;\nselp.u32 %0, 1, 0, p;\n}" : "=r"(p));
  return p;
}
__device__ __forceinline__ void mbar_arrive_if(bool p, uint32_t bar) {
  asm volatile("{\n.reg .pred p;\nsetp.ne.b32 p, %1, 0;\n@p mbarrier.arrive.shared::cta.b64 _, [%0];\n}" ::"r"(bar), "r"((int)p) : "memory");
}
__device__ __forceinline__ void hint_add_if(bool p, unsigned* a) {
  asm volatile("{\n.reg .pred p;\nsetp.ne.b32 p, %1, 0;\n@p red.relaxed.gpu.global.add.u32 [%0], 1;\n}" ::"l"(a), "r"((int)p) : "memory");
}
__device__ __forceinline__ bool mbar_try(uint32_t bar, uint32_t parity) {
  uint32_t ok;
  asm volatile("{\n.reg .pred p;\nmbarrier.test_wait.parity.shared::cta.b64 p, [%1], %2;\nselp.u32 %0, 1, 0, p;\n}" : "=r"(ok) : "r"(bar), "r"(parity) : "memory");
  return ok;
}
__device__ __forceinline__ void mbar_wait(uint32_t bar, uint32_t parity) {
  asm volatile(
      "{\n.reg .pred p;\n.reg .u32 n;\nmov.u32 n, 0;\n"
      "W_LOOP:\nmbarrier.try_wait.parity.shared::cta.b64 p, [%0], %1;\n@p bra W_DONE;\n"
      "add.u32 n, n, 1;\nsetp.lt.u32 p, n, 0x40000;\n@p bra W_LOOP;\ntrap;\nW_DONE:\n}" ::"r"(bar), "r"(parity) : "memory");
}
__device__ __forceinline__ void bulk_load(uint32_t dst, const void* src, uint32_t bytes, uint32_t bar) {
  asm volatile("cp.async.bulk.shared::cluster.global.mbarrier::complete_tx::bytes [%0], [%1], %2, [%3];" ::"r"(dst), "l"(src), "r"(bytes), "r"(bar) : "memory");
}
__device__ __forceinline__ void cp16(uint32_t dst, const void* src) { asm volatile("cp.async.cg.shared.global [%0], [%1], 16;" ::"r"(dst), "l"(src) : "memory"); }
__device__ __forceinline__ void spin_guard(uint32_t t0) { if ((uint32_t)clock() - t0 > (1u << 30)) __trap(); }
__device__ __forceinline__ float tagf(float v, uint32_t tag) { return __uint_as_float((__float_as_uint(v) & ~1u) | tag); }
__device__ __forceinline__ float untag(float v) { return __uint_as_float(__float_as_uint(v) & ~1u); }
__device__ __forceinline__ void st_x2(float2* p, float a, float b) { asm volatile("st.relaxed.gpu.global.v2.f32 [%0], {%1,%2};" ::"l"(p), "f"(a), "f"(b) : "memory"); }
__device__ __forceinline__ float2 ld_x2(const float2* p) { float2 v; asm volatile("ld.relaxed.gpu.global.v2.f32 {%0,%1}, [%2];" : "=f"(v.x), "=f"(v.y) : "l"(p) : "memory"); return v; }
__device__ __forceinline__ void st_u2(uint2* p, uint32_t a, uint32_t b) { asm volatile("st.relaxed.gpu.global.v2.u32 [%0], {%1,%2};" ::"l"(p), "r"(a), "r"(b) : "memory"); }
__device__ __forceinline__ void prefetch2d(const CUtensorMap* m, int c0, int c1) { asm volatile("cp.async.bulk.prefetch.tensor.2d.L2.global [%0, {%1, %2}];" ::"l"(m), "r"(c0), "r"(c1) : "memory"); }
__device__ __forceinline__ void prefetch1d(const void* p, uint32_t bytes) { asm volatile("cp.async.bulk.prefetch.L2.global [%0], %1;" ::"l"(p), "r"(bytes) : "memory"); }
__device__ __forceinline__ uint32_t ld_x1(const void* p) { uint32_t v; asm volatile("ld.relaxed.gpu.global.u32 %0, [%1];" : "=r"(v) : "l"(p) : "memory"); return v; }
__device__ __forceinline__ uint4 ld_x4(const void* p) { uint4 v; asm volatile("ld.relaxed.gpu.global.v4.u32 {%0,%1,%2,%3}, [%4];" : "=r"(v.x), "=r"(v.y), "=r"(v.z), "=r"(v.w) : "l"(p) : "memory"); return v; }
__device__ __forceinline__ void st_x4(void* p, uint32_t a, uint32_t b, uint32_t c, uint32_t d) { asm volatile("st.relaxed.gpu.global.v4.u32 [%0], {%1,%2,%3,%4};" ::"l"(p), "r"(a), "r"(b), "r"(c), "r"(d) : "memory"); }
__device__ __forceinline__ uint32_t mapa(uint32_t a, uint32_t cta) { uint32_t r; asm volatile("mapa.shared::cluster.u32 %0, %1, %2;" : "=r"(r) : "r"(a), "r"(cta)); return r; }
__device__ __forceinline__ void stsm4t(uint32_t a, uint32_t r0, uint32_t r1, uint32_t r2, uint32_t r3) {
  asm volatile("stmatrix.sync.aligned.m8n8.x4.trans.shared.b16 [%0], {%1,%2,%3,%4};" ::"r"(a), "r"(r0), "r"(r1), "r"(r2), "r"(r3) : "memory");
}
__device__ __forceinline__ void hint_add(unsigned* p) { asm volatile("red.relaxed.gpu.global.add.u32 [%0], 1;" ::"l"(p) : "memory"); }
__device__ __forceinline__ void hint_wait(const unsigned* p, unsigned target) {
  const uint32_t t0 = (uint32_t)clock();
  while ((int)(ld_x1(p) - target) < 0) spin_guard(t0);
}
__device__ __forceinline__ void bulk_done_signal(unsigned* p) {
  asm volatile("cp.async.bulk.commit_group;\ncp.async.bulk.wait_group 0;\nfence.proxy.async.global;" ::: "memory");
  hint_add(p);
}
__device__ __forceinline__ void flag_wait(const unsigned* p, unsigned target) {
  hint_wait(p, target);
  asm volatile("fence.proxy.async.global;" ::: "memory");
}
__device__ __forceinline__ void tma2d(uint32_t dst, const CUtensorMap* m, uint32_t bar, int c0, int c1) {
  asm volatile("cp.async.bulk.tensor.2d.shared::cluster.global.mbarrier::complete_tx::bytes [%0], [%1, {%3, %4}], [%2];" ::"r"(dst), "l"(m), "r"(bar), "r"(c0), "r"(c1) : "memory");
}
__device__ __forceinline__ void tma3d(uint32_t dst, const CUtensorMap* m, uint32_t bar, int c0, int c1, int c2) {
  asm volatile("cp.async.bulk.tensor.3d.shared::cluster.global.mbarrier::complete_tx::bytes [%0], [%1, {%3, %4, %5}], [%2];" ::"r"(dst), "l"(m), "r"(bar), "r"(c0), "r"(c1), "r"(c2) : "memory");
}
__device__ __forceinline__ void tma4d(uint32_t dst, const CUtensorMap* m, uint32_t bar, int c0, int c1, int c2, int c3) {
  asm volatile("cp.async.bulk.tensor.4d.shared::cluster.global.mbarrier::complete_tx::bytes [%0], [%1, {%3, %4, %5, %6}], [%2];" ::"r"(dst), "l"(m), "r"(bar), "r"(c0), "r"(c1), "r"(c2), "r"(c3) : "memory");
}
__device__ __forceinline__ void wg_fence() { asm volatile("wgmma.fence.sync.aligned;" ::: "memory"); }
__device__ __forceinline__ void wg_commit() { asm volatile("wgmma.commit_group.sync.aligned;" ::: "memory"); }
template <int N> __device__ __forceinline__ void wg_wait() { asm volatile("wgmma.wait_group.sync.aligned %0;" ::"n"(N) : "memory"); }
template <int O, int N, int NN> __device__ __forceinline__ void fence_regs(float (&d)[NN]) {
#pragma unroll
  for (int i = 0; i < N; i++) asm volatile("" : "+f"(d[O + i])::"memory");
}
__device__ __forceinline__ uint32_t pack_bf16(float lo, float hi) {
  uint32_t r; asm("cvt.rn.bf16x2.f32 %0, %1, %2;" : "=r"(r) : "f"(hi), "f"(lo)); return r;
}
__device__ __forceinline__ uint32_t pack_pin(float lo, float hi) {
  uint32_t r; asm volatile("cvt.rn.bf16x2.f32 %0, %1, %2;" : "=r"(r) : "f"(hi), "f"(lo) : "memory"); return r;
}
__device__ __forceinline__ float bf_lo(uint32_t u) { return __uint_as_float(u << 16); }
__device__ __forceinline__ float bf_hi(uint32_t u) { return __uint_as_float(u & 0xffff0000u); }

__device__ __forceinline__ uint64_t d128(uint32_t lo) { uint64_t d; asm("mov.b64 %0, {%1, 0x40000040};" : "=l"(d) : "r"(lo)); return d; }
__device__ __forceinline__ uint64_t d64(uint32_t lo) { uint64_t d; asm("mov.b64 %0, {%1, 0x80000020};" : "=l"(d) : "r"(lo)); return d; }
template<int O,int TB,int ACC,int NN> __device__ __forceinline__ void mma_ss64(float (&d)[NN], uint64_t da, uint64_t db, int sd = 0){
  if constexpr (ACC == 1) asm volatile("wgmma.mma_async.sync.aligned.m64n64k16.f32.bf16.bf16 {%0,%1,%2,%3,%4,%5,%6,%7,%8,%9,%10,%11,%12,%13,%14,%15,%16,%17,%18,%19,%20,%21,%22,%23,%24,%25,%26,%27,%28,%29,%30,%31}, %32, %33, 1, 1, 1, %35, %34;"
   : "+f"(d[O+0]), "+f"(d[O+1]), "+f"(d[O+2]), "+f"(d[O+3]), "+f"(d[O+4]), "+f"(d[O+5]), "+f"(d[O+6]), "+f"(d[O+7]), "+f"(d[O+8]), "+f"(d[O+9]), "+f"(d[O+10]), "+f"(d[O+11]), "+f"(d[O+12]), "+f"(d[O+13]), "+f"(d[O+14]), "+f"(d[O+15]), "+f"(d[O+16]), "+f"(d[O+17]), "+f"(d[O+18]), "+f"(d[O+19]), "+f"(d[O+20]), "+f"(d[O+21]), "+f"(d[O+22]), "+f"(d[O+23]), "+f"(d[O+24]), "+f"(d[O+25]), "+f"(d[O+26]), "+f"(d[O+27]), "+f"(d[O+28]), "+f"(d[O+29]), "+f"(d[O+30]), "+f"(d[O+31])
   : "l"(da), "l"(db), "n"(TB & 1), "n"(TB >> 1));
  else if constexpr (ACC == 0) asm volatile("wgmma.mma_async.sync.aligned.m64n64k16.f32.bf16.bf16 {%0,%1,%2,%3,%4,%5,%6,%7,%8,%9,%10,%11,%12,%13,%14,%15,%16,%17,%18,%19,%20,%21,%22,%23,%24,%25,%26,%27,%28,%29,%30,%31}, %32, %33, 0, 1, 1, %35, %34;"
   : "=f"(d[O+0]), "=f"(d[O+1]), "=f"(d[O+2]), "=f"(d[O+3]), "=f"(d[O+4]), "=f"(d[O+5]), "=f"(d[O+6]), "=f"(d[O+7]), "=f"(d[O+8]), "=f"(d[O+9]), "=f"(d[O+10]), "=f"(d[O+11]), "=f"(d[O+12]), "=f"(d[O+13]), "=f"(d[O+14]), "=f"(d[O+15]), "=f"(d[O+16]), "=f"(d[O+17]), "=f"(d[O+18]), "=f"(d[O+19]), "=f"(d[O+20]), "=f"(d[O+21]), "=f"(d[O+22]), "=f"(d[O+23]), "=f"(d[O+24]), "=f"(d[O+25]), "=f"(d[O+26]), "=f"(d[O+27]), "=f"(d[O+28]), "=f"(d[O+29]), "=f"(d[O+30]), "=f"(d[O+31])
   : "l"(da), "l"(db), "n"(TB & 1), "n"(TB >> 1));
  else asm volatile("{\n.reg .pred p;\nsetp.ne.b32 p, %36, 0;\nwgmma.mma_async.sync.aligned.m64n64k16.f32.bf16.bf16 {%0,%1,%2,%3,%4,%5,%6,%7,%8,%9,%10,%11,%12,%13,%14,%15,%16,%17,%18,%19,%20,%21,%22,%23,%24,%25,%26,%27,%28,%29,%30,%31}, %32, %33, p, 1, 1, %35, %34;\n}"
   : "+f"(d[O+0]), "+f"(d[O+1]), "+f"(d[O+2]), "+f"(d[O+3]), "+f"(d[O+4]), "+f"(d[O+5]), "+f"(d[O+6]), "+f"(d[O+7]), "+f"(d[O+8]), "+f"(d[O+9]), "+f"(d[O+10]), "+f"(d[O+11]), "+f"(d[O+12]), "+f"(d[O+13]), "+f"(d[O+14]), "+f"(d[O+15]), "+f"(d[O+16]), "+f"(d[O+17]), "+f"(d[O+18]), "+f"(d[O+19]), "+f"(d[O+20]), "+f"(d[O+21]), "+f"(d[O+22]), "+f"(d[O+23]), "+f"(d[O+24]), "+f"(d[O+25]), "+f"(d[O+26]), "+f"(d[O+27]), "+f"(d[O+28]), "+f"(d[O+29]), "+f"(d[O+30]), "+f"(d[O+31])
   : "l"(da), "l"(db), "n"(TB & 1), "n"(TB >> 1), "r"(sd));
}
template<int O,int TB,int ACC,int NN> __device__ __forceinline__ void mma_rs64(float (&d)[NN], uint32_t a0, uint32_t a1, uint32_t a2, uint32_t a3, uint64_t db, int sd = 0){
  if constexpr (ACC == 1) asm volatile("wgmma.mma_async.sync.aligned.m64n64k16.f32.bf16.bf16 {%0,%1,%2,%3,%4,%5,%6,%7,%8,%9,%10,%11,%12,%13,%14,%15,%16,%17,%18,%19,%20,%21,%22,%23,%24,%25,%26,%27,%28,%29,%30,%31}, {%32,%33,%34,%35}, %36, 1, 1, 1, %37;"
   : "+f"(d[O+0]), "+f"(d[O+1]), "+f"(d[O+2]), "+f"(d[O+3]), "+f"(d[O+4]), "+f"(d[O+5]), "+f"(d[O+6]), "+f"(d[O+7]), "+f"(d[O+8]), "+f"(d[O+9]), "+f"(d[O+10]), "+f"(d[O+11]), "+f"(d[O+12]), "+f"(d[O+13]), "+f"(d[O+14]), "+f"(d[O+15]), "+f"(d[O+16]), "+f"(d[O+17]), "+f"(d[O+18]), "+f"(d[O+19]), "+f"(d[O+20]), "+f"(d[O+21]), "+f"(d[O+22]), "+f"(d[O+23]), "+f"(d[O+24]), "+f"(d[O+25]), "+f"(d[O+26]), "+f"(d[O+27]), "+f"(d[O+28]), "+f"(d[O+29]), "+f"(d[O+30]), "+f"(d[O+31])
   : "r"(a0), "r"(a1), "r"(a2), "r"(a3), "l"(db), "n"(TB));
  else if constexpr (ACC == 0) asm volatile("wgmma.mma_async.sync.aligned.m64n64k16.f32.bf16.bf16 {%0,%1,%2,%3,%4,%5,%6,%7,%8,%9,%10,%11,%12,%13,%14,%15,%16,%17,%18,%19,%20,%21,%22,%23,%24,%25,%26,%27,%28,%29,%30,%31}, {%32,%33,%34,%35}, %36, 0, 1, 1, %37;"
   : "=f"(d[O+0]), "=f"(d[O+1]), "=f"(d[O+2]), "=f"(d[O+3]), "=f"(d[O+4]), "=f"(d[O+5]), "=f"(d[O+6]), "=f"(d[O+7]), "=f"(d[O+8]), "=f"(d[O+9]), "=f"(d[O+10]), "=f"(d[O+11]), "=f"(d[O+12]), "=f"(d[O+13]), "=f"(d[O+14]), "=f"(d[O+15]), "=f"(d[O+16]), "=f"(d[O+17]), "=f"(d[O+18]), "=f"(d[O+19]), "=f"(d[O+20]), "=f"(d[O+21]), "=f"(d[O+22]), "=f"(d[O+23]), "=f"(d[O+24]), "=f"(d[O+25]), "=f"(d[O+26]), "=f"(d[O+27]), "=f"(d[O+28]), "=f"(d[O+29]), "=f"(d[O+30]), "=f"(d[O+31])
   : "r"(a0), "r"(a1), "r"(a2), "r"(a3), "l"(db), "n"(TB));
  else asm volatile("{\n.reg .pred p;\nsetp.ne.b32 p, %38, 0;\nwgmma.mma_async.sync.aligned.m64n64k16.f32.bf16.bf16 {%0,%1,%2,%3,%4,%5,%6,%7,%8,%9,%10,%11,%12,%13,%14,%15,%16,%17,%18,%19,%20,%21,%22,%23,%24,%25,%26,%27,%28,%29,%30,%31}, {%32,%33,%34,%35}, %36, p, 1, 1, %37;\n}"
   : "+f"(d[O+0]), "+f"(d[O+1]), "+f"(d[O+2]), "+f"(d[O+3]), "+f"(d[O+4]), "+f"(d[O+5]), "+f"(d[O+6]), "+f"(d[O+7]), "+f"(d[O+8]), "+f"(d[O+9]), "+f"(d[O+10]), "+f"(d[O+11]), "+f"(d[O+12]), "+f"(d[O+13]), "+f"(d[O+14]), "+f"(d[O+15]), "+f"(d[O+16]), "+f"(d[O+17]), "+f"(d[O+18]), "+f"(d[O+19]), "+f"(d[O+20]), "+f"(d[O+21]), "+f"(d[O+22]), "+f"(d[O+23]), "+f"(d[O+24]), "+f"(d[O+25]), "+f"(d[O+26]), "+f"(d[O+27]), "+f"(d[O+28]), "+f"(d[O+29]), "+f"(d[O+30]), "+f"(d[O+31])
   : "r"(a0), "r"(a1), "r"(a2), "r"(a3), "l"(db), "n"(TB), "r"(sd));
}
template<int O,int TB,int ACC,int NN> __device__ __forceinline__ void mma_ss128(float (&d)[NN], uint64_t da, uint64_t db, int sd = 0){
  if constexpr (ACC == 1) asm volatile("wgmma.mma_async.sync.aligned.m64n128k16.f32.bf16.bf16 {%0,%1,%2,%3,%4,%5,%6,%7,%8,%9,%10,%11,%12,%13,%14,%15,%16,%17,%18,%19,%20,%21,%22,%23,%24,%25,%26,%27,%28,%29,%30,%31,%32,%33,%34,%35,%36,%37,%38,%39,%40,%41,%42,%43,%44,%45,%46,%47,%48,%49,%50,%51,%52,%53,%54,%55,%56,%57,%58,%59,%60,%61,%62,%63}, %64, %65, 1, 1, 1, %67, %66;"
   : "+f"(d[O+0]), "+f"(d[O+1]), "+f"(d[O+2]), "+f"(d[O+3]), "+f"(d[O+4]), "+f"(d[O+5]), "+f"(d[O+6]), "+f"(d[O+7]), "+f"(d[O+8]), "+f"(d[O+9]), "+f"(d[O+10]), "+f"(d[O+11]), "+f"(d[O+12]), "+f"(d[O+13]), "+f"(d[O+14]), "+f"(d[O+15]), "+f"(d[O+16]), "+f"(d[O+17]), "+f"(d[O+18]), "+f"(d[O+19]), "+f"(d[O+20]), "+f"(d[O+21]), "+f"(d[O+22]), "+f"(d[O+23]), "+f"(d[O+24]), "+f"(d[O+25]), "+f"(d[O+26]), "+f"(d[O+27]), "+f"(d[O+28]), "+f"(d[O+29]), "+f"(d[O+30]), "+f"(d[O+31]), "+f"(d[O+32]), "+f"(d[O+33]), "+f"(d[O+34]), "+f"(d[O+35]), "+f"(d[O+36]), "+f"(d[O+37]), "+f"(d[O+38]), "+f"(d[O+39]), "+f"(d[O+40]), "+f"(d[O+41]), "+f"(d[O+42]), "+f"(d[O+43]), "+f"(d[O+44]), "+f"(d[O+45]), "+f"(d[O+46]), "+f"(d[O+47]), "+f"(d[O+48]), "+f"(d[O+49]), "+f"(d[O+50]), "+f"(d[O+51]), "+f"(d[O+52]), "+f"(d[O+53]), "+f"(d[O+54]), "+f"(d[O+55]), "+f"(d[O+56]), "+f"(d[O+57]), "+f"(d[O+58]), "+f"(d[O+59]), "+f"(d[O+60]), "+f"(d[O+61]), "+f"(d[O+62]), "+f"(d[O+63])
   : "l"(da), "l"(db), "n"(TB & 1), "n"(TB >> 1));
  else if constexpr (ACC == 0) asm volatile("wgmma.mma_async.sync.aligned.m64n128k16.f32.bf16.bf16 {%0,%1,%2,%3,%4,%5,%6,%7,%8,%9,%10,%11,%12,%13,%14,%15,%16,%17,%18,%19,%20,%21,%22,%23,%24,%25,%26,%27,%28,%29,%30,%31,%32,%33,%34,%35,%36,%37,%38,%39,%40,%41,%42,%43,%44,%45,%46,%47,%48,%49,%50,%51,%52,%53,%54,%55,%56,%57,%58,%59,%60,%61,%62,%63}, %64, %65, 0, 1, 1, %67, %66;"
   : "=f"(d[O+0]), "=f"(d[O+1]), "=f"(d[O+2]), "=f"(d[O+3]), "=f"(d[O+4]), "=f"(d[O+5]), "=f"(d[O+6]), "=f"(d[O+7]), "=f"(d[O+8]), "=f"(d[O+9]), "=f"(d[O+10]), "=f"(d[O+11]), "=f"(d[O+12]), "=f"(d[O+13]), "=f"(d[O+14]), "=f"(d[O+15]), "=f"(d[O+16]), "=f"(d[O+17]), "=f"(d[O+18]), "=f"(d[O+19]), "=f"(d[O+20]), "=f"(d[O+21]), "=f"(d[O+22]), "=f"(d[O+23]), "=f"(d[O+24]), "=f"(d[O+25]), "=f"(d[O+26]), "=f"(d[O+27]), "=f"(d[O+28]), "=f"(d[O+29]), "=f"(d[O+30]), "=f"(d[O+31]), "=f"(d[O+32]), "=f"(d[O+33]), "=f"(d[O+34]), "=f"(d[O+35]), "=f"(d[O+36]), "=f"(d[O+37]), "=f"(d[O+38]), "=f"(d[O+39]), "=f"(d[O+40]), "=f"(d[O+41]), "=f"(d[O+42]), "=f"(d[O+43]), "=f"(d[O+44]), "=f"(d[O+45]), "=f"(d[O+46]), "=f"(d[O+47]), "=f"(d[O+48]), "=f"(d[O+49]), "=f"(d[O+50]), "=f"(d[O+51]), "=f"(d[O+52]), "=f"(d[O+53]), "=f"(d[O+54]), "=f"(d[O+55]), "=f"(d[O+56]), "=f"(d[O+57]), "=f"(d[O+58]), "=f"(d[O+59]), "=f"(d[O+60]), "=f"(d[O+61]), "=f"(d[O+62]), "=f"(d[O+63])
   : "l"(da), "l"(db), "n"(TB & 1), "n"(TB >> 1));
  else asm volatile("{\n.reg .pred p;\nsetp.ne.b32 p, %68, 0;\nwgmma.mma_async.sync.aligned.m64n128k16.f32.bf16.bf16 {%0,%1,%2,%3,%4,%5,%6,%7,%8,%9,%10,%11,%12,%13,%14,%15,%16,%17,%18,%19,%20,%21,%22,%23,%24,%25,%26,%27,%28,%29,%30,%31,%32,%33,%34,%35,%36,%37,%38,%39,%40,%41,%42,%43,%44,%45,%46,%47,%48,%49,%50,%51,%52,%53,%54,%55,%56,%57,%58,%59,%60,%61,%62,%63}, %64, %65, p, 1, 1, %67, %66;\n}"
   : "+f"(d[O+0]), "+f"(d[O+1]), "+f"(d[O+2]), "+f"(d[O+3]), "+f"(d[O+4]), "+f"(d[O+5]), "+f"(d[O+6]), "+f"(d[O+7]), "+f"(d[O+8]), "+f"(d[O+9]), "+f"(d[O+10]), "+f"(d[O+11]), "+f"(d[O+12]), "+f"(d[O+13]), "+f"(d[O+14]), "+f"(d[O+15]), "+f"(d[O+16]), "+f"(d[O+17]), "+f"(d[O+18]), "+f"(d[O+19]), "+f"(d[O+20]), "+f"(d[O+21]), "+f"(d[O+22]), "+f"(d[O+23]), "+f"(d[O+24]), "+f"(d[O+25]), "+f"(d[O+26]), "+f"(d[O+27]), "+f"(d[O+28]), "+f"(d[O+29]), "+f"(d[O+30]), "+f"(d[O+31]), "+f"(d[O+32]), "+f"(d[O+33]), "+f"(d[O+34]), "+f"(d[O+35]), "+f"(d[O+36]), "+f"(d[O+37]), "+f"(d[O+38]), "+f"(d[O+39]), "+f"(d[O+40]), "+f"(d[O+41]), "+f"(d[O+42]), "+f"(d[O+43]), "+f"(d[O+44]), "+f"(d[O+45]), "+f"(d[O+46]), "+f"(d[O+47]), "+f"(d[O+48]), "+f"(d[O+49]), "+f"(d[O+50]), "+f"(d[O+51]), "+f"(d[O+52]), "+f"(d[O+53]), "+f"(d[O+54]), "+f"(d[O+55]), "+f"(d[O+56]), "+f"(d[O+57]), "+f"(d[O+58]), "+f"(d[O+59]), "+f"(d[O+60]), "+f"(d[O+61]), "+f"(d[O+62]), "+f"(d[O+63])
   : "l"(da), "l"(db), "n"(TB & 1), "n"(TB >> 1), "r"(sd));
}
template<int O,int TB,int ACC,int NN> __device__ __forceinline__ void mma_rs128(float (&d)[NN], uint32_t a0, uint32_t a1, uint32_t a2, uint32_t a3, uint64_t db, int sd = 0){
  if constexpr (ACC == 1) asm volatile("wgmma.mma_async.sync.aligned.m64n128k16.f32.bf16.bf16 {%0,%1,%2,%3,%4,%5,%6,%7,%8,%9,%10,%11,%12,%13,%14,%15,%16,%17,%18,%19,%20,%21,%22,%23,%24,%25,%26,%27,%28,%29,%30,%31,%32,%33,%34,%35,%36,%37,%38,%39,%40,%41,%42,%43,%44,%45,%46,%47,%48,%49,%50,%51,%52,%53,%54,%55,%56,%57,%58,%59,%60,%61,%62,%63}, {%64,%65,%66,%67}, %68, 1, 1, 1, %69;"
   : "+f"(d[O+0]), "+f"(d[O+1]), "+f"(d[O+2]), "+f"(d[O+3]), "+f"(d[O+4]), "+f"(d[O+5]), "+f"(d[O+6]), "+f"(d[O+7]), "+f"(d[O+8]), "+f"(d[O+9]), "+f"(d[O+10]), "+f"(d[O+11]), "+f"(d[O+12]), "+f"(d[O+13]), "+f"(d[O+14]), "+f"(d[O+15]), "+f"(d[O+16]), "+f"(d[O+17]), "+f"(d[O+18]), "+f"(d[O+19]), "+f"(d[O+20]), "+f"(d[O+21]), "+f"(d[O+22]), "+f"(d[O+23]), "+f"(d[O+24]), "+f"(d[O+25]), "+f"(d[O+26]), "+f"(d[O+27]), "+f"(d[O+28]), "+f"(d[O+29]), "+f"(d[O+30]), "+f"(d[O+31]), "+f"(d[O+32]), "+f"(d[O+33]), "+f"(d[O+34]), "+f"(d[O+35]), "+f"(d[O+36]), "+f"(d[O+37]), "+f"(d[O+38]), "+f"(d[O+39]), "+f"(d[O+40]), "+f"(d[O+41]), "+f"(d[O+42]), "+f"(d[O+43]), "+f"(d[O+44]), "+f"(d[O+45]), "+f"(d[O+46]), "+f"(d[O+47]), "+f"(d[O+48]), "+f"(d[O+49]), "+f"(d[O+50]), "+f"(d[O+51]), "+f"(d[O+52]), "+f"(d[O+53]), "+f"(d[O+54]), "+f"(d[O+55]), "+f"(d[O+56]), "+f"(d[O+57]), "+f"(d[O+58]), "+f"(d[O+59]), "+f"(d[O+60]), "+f"(d[O+61]), "+f"(d[O+62]), "+f"(d[O+63])
   : "r"(a0), "r"(a1), "r"(a2), "r"(a3), "l"(db), "n"(TB));
  else if constexpr (ACC == 0) asm volatile("wgmma.mma_async.sync.aligned.m64n128k16.f32.bf16.bf16 {%0,%1,%2,%3,%4,%5,%6,%7,%8,%9,%10,%11,%12,%13,%14,%15,%16,%17,%18,%19,%20,%21,%22,%23,%24,%25,%26,%27,%28,%29,%30,%31,%32,%33,%34,%35,%36,%37,%38,%39,%40,%41,%42,%43,%44,%45,%46,%47,%48,%49,%50,%51,%52,%53,%54,%55,%56,%57,%58,%59,%60,%61,%62,%63}, {%64,%65,%66,%67}, %68, 0, 1, 1, %69;"
   : "=f"(d[O+0]), "=f"(d[O+1]), "=f"(d[O+2]), "=f"(d[O+3]), "=f"(d[O+4]), "=f"(d[O+5]), "=f"(d[O+6]), "=f"(d[O+7]), "=f"(d[O+8]), "=f"(d[O+9]), "=f"(d[O+10]), "=f"(d[O+11]), "=f"(d[O+12]), "=f"(d[O+13]), "=f"(d[O+14]), "=f"(d[O+15]), "=f"(d[O+16]), "=f"(d[O+17]), "=f"(d[O+18]), "=f"(d[O+19]), "=f"(d[O+20]), "=f"(d[O+21]), "=f"(d[O+22]), "=f"(d[O+23]), "=f"(d[O+24]), "=f"(d[O+25]), "=f"(d[O+26]), "=f"(d[O+27]), "=f"(d[O+28]), "=f"(d[O+29]), "=f"(d[O+30]), "=f"(d[O+31]), "=f"(d[O+32]), "=f"(d[O+33]), "=f"(d[O+34]), "=f"(d[O+35]), "=f"(d[O+36]), "=f"(d[O+37]), "=f"(d[O+38]), "=f"(d[O+39]), "=f"(d[O+40]), "=f"(d[O+41]), "=f"(d[O+42]), "=f"(d[O+43]), "=f"(d[O+44]), "=f"(d[O+45]), "=f"(d[O+46]), "=f"(d[O+47]), "=f"(d[O+48]), "=f"(d[O+49]), "=f"(d[O+50]), "=f"(d[O+51]), "=f"(d[O+52]), "=f"(d[O+53]), "=f"(d[O+54]), "=f"(d[O+55]), "=f"(d[O+56]), "=f"(d[O+57]), "=f"(d[O+58]), "=f"(d[O+59]), "=f"(d[O+60]), "=f"(d[O+61]), "=f"(d[O+62]), "=f"(d[O+63])
   : "r"(a0), "r"(a1), "r"(a2), "r"(a3), "l"(db), "n"(TB));
  else asm volatile("{\n.reg .pred p;\nsetp.ne.b32 p, %70, 0;\nwgmma.mma_async.sync.aligned.m64n128k16.f32.bf16.bf16 {%0,%1,%2,%3,%4,%5,%6,%7,%8,%9,%10,%11,%12,%13,%14,%15,%16,%17,%18,%19,%20,%21,%22,%23,%24,%25,%26,%27,%28,%29,%30,%31,%32,%33,%34,%35,%36,%37,%38,%39,%40,%41,%42,%43,%44,%45,%46,%47,%48,%49,%50,%51,%52,%53,%54,%55,%56,%57,%58,%59,%60,%61,%62,%63}, {%64,%65,%66,%67}, %68, p, 1, 1, %69;\n}"
   : "+f"(d[O+0]), "+f"(d[O+1]), "+f"(d[O+2]), "+f"(d[O+3]), "+f"(d[O+4]), "+f"(d[O+5]), "+f"(d[O+6]), "+f"(d[O+7]), "+f"(d[O+8]), "+f"(d[O+9]), "+f"(d[O+10]), "+f"(d[O+11]), "+f"(d[O+12]), "+f"(d[O+13]), "+f"(d[O+14]), "+f"(d[O+15]), "+f"(d[O+16]), "+f"(d[O+17]), "+f"(d[O+18]), "+f"(d[O+19]), "+f"(d[O+20]), "+f"(d[O+21]), "+f"(d[O+22]), "+f"(d[O+23]), "+f"(d[O+24]), "+f"(d[O+25]), "+f"(d[O+26]), "+f"(d[O+27]), "+f"(d[O+28]), "+f"(d[O+29]), "+f"(d[O+30]), "+f"(d[O+31]), "+f"(d[O+32]), "+f"(d[O+33]), "+f"(d[O+34]), "+f"(d[O+35]), "+f"(d[O+36]), "+f"(d[O+37]), "+f"(d[O+38]), "+f"(d[O+39]), "+f"(d[O+40]), "+f"(d[O+41]), "+f"(d[O+42]), "+f"(d[O+43]), "+f"(d[O+44]), "+f"(d[O+45]), "+f"(d[O+46]), "+f"(d[O+47]), "+f"(d[O+48]), "+f"(d[O+49]), "+f"(d[O+50]), "+f"(d[O+51]), "+f"(d[O+52]), "+f"(d[O+53]), "+f"(d[O+54]), "+f"(d[O+55]), "+f"(d[O+56]), "+f"(d[O+57]), "+f"(d[O+58]), "+f"(d[O+59]), "+f"(d[O+60]), "+f"(d[O+61]), "+f"(d[O+62]), "+f"(d[O+63])
   : "r"(a0), "r"(a1), "r"(a2), "r"(a3), "l"(db), "n"(TB), "r"(sd));
}

#define NEARLY 0
#define XAHEAD 3
#define HEADN 6
#define WBATCH 1
#define WB 8
#define WSLEEP 20
#define XSPREAD 4
#define NOSEND 0
#define MSPLIT 3
#define PFALL 1
#define L2PF 1
#define STAG 0
#define EPF 2
#define XNB 2
#define FNB 0
#define GNB 0
#define TH 5
#define PF0 4
#define SPACE 40
#define WPF 1
#define WAFTER 7
#define WPACE 0
#define GATE_AT 4
#define TPACE 40
#define PFMODE 0
#define MAPMODE 1
template <int V> struct IC { static constexpr int value = V; };
struct Maps { CUtensorMap x, ft, g64, u64, e, wr, wi, xs, ts, t, g32, u32, d224, o; };

constexpr int NCTA = 130;
constexpr int U = 16384;
constexpr int TB = 36864;
constexpr int OFF_RING = 8 * U, OFF_Z = 9 * U, OFF_XB = 12 * U, OFF_T = 13 * U, OFF_D = OFF_T;
constexpr int OFF_BAR = 14 * U, OFF_SP = OFF_BAR + 512, OFF_G = OFF_SP + 1024 + 128;
constexpr int SMEM_BYTES = OFF_G + 512;
constexpr int B_FX = 0, B_FA = 8, B_FT = 12, B_Z = 16, B_W = 24, B_HX = 25, B_TL = 26, B_HP = 27, B_WR = 30, B_E0 = 34;
constexpr int B_EA = 35, B_ET = 39, B_PZ = 43, B_RDY = 45, B_FE = 46;
constexpr int B_T = 50, B_XS = 51, B_G = 53, NBAR = 54;
__host__ __device__ constexpr int rslot(int n) { return n & 3; }
__host__ __device__ constexpr int rpar(int n) { return (n >> 2) & 1; }

__global__ void __cluster_dims__(2, 1, 1) __launch_bounds__(512, 1)
fused_kernel(Work* __restrict__ ws, const uint16_t* __restrict__ dtab, const __nv_bfloat16* __restrict__ w_r, const __nv_bfloat16* __restrict__ w_i,
             const __nv_bfloat16* __restrict__ gate_w, const __nv_bfloat16* __restrict__ x, const uint16_t* __restrict__ ftab,
             const __nv_bfloat16* __restrict__ Wg, const __nv_bfloat16* __restrict__ Wu, const __grid_constant__ Maps maps) {
  extern __shared__ __align__(1024) uint8_t smem[];
  if (threadIdx.x < 32 && elect_one()) {
#pragma unroll
    for (int i = 0; i < PF0; i++) asm volatile("prefetch.tensormap [%0];" ::"l"((const char*)&maps + i * 128) : "memory");
  }
  const uint32_t sb = smem_u32(smem);
  const uint32_t bars = sb + OFF_BAR;
  const int tid = threadIdx.x, lane = tid & 31;
  const int warp = __shfl_sync(0xffffffffu, tid >> 5, 0);
  const bool helper = blockIdx.x >= 128;
  const int cl = (blockIdx.x >> 1) & 63, rank = blockIdx.x & 1;
  const int q4 = (cl & 1) | ((cl >> 2) & 2), rb = ((cl >> 1) & 3) | ((cl >> 4) << 2);
  const int j = 2 * q4 + rank;
  const int f_full = 448 * q4 + (rank ? 256 : 0);
  const int f_half = 448 * q4 + (rank ? 224 : 192);
  const int kg = 2 * j + (rb >> 3), tn = rb & 7;

  if (tid == 64) { PROF_EV(0); PROF_CK(40); }
  if (warp < 8) {
    if (!helper) {
      if (tid < 16 * XNB) {
        const int r = 16 * j + (tid & 15);
        asm volatile("prefetch.global.L2 [%0];" ::"l"(x + (size_t)(2 * rb + (r >> 6) + 32 * (r & 63)) * 512 + 64 * (tid >> 4)));
      } else if (tid >= 128 && tid < 128 + 4 * FNB) {
        asm volatile("prefetch.global.L2 [%0];" ::"l"(ftab + (64 * j + 4 * rb + (tid & 3)) * 512 + 64 * ((tid - 128) >> 2)));
      } else if (tid >= 192 && tid < 192 + 8 * GNB) {
        asm volatile("prefetch.global.L2 [%0];" ::"l"(((tid & 4) ? Wu : Wg) + (size_t)(64 * ((tid - 192) >> 3) + 4 * rb + (tid & 3)) * 1792 + f_full));
      }
    }
    asm volatile("barrier.cluster.arrive.relaxed.aligned;" ::: "memory");
    asm volatile("setmaxnreg.inc.sync.aligned.u32 192;");
    if (!helper) {
      const int wg = warp >> 2, w = warp & 3, g = lane >> 2;
      const bool elect = (tid & 127) == 0;
      float cX[32], cA[64], cB[64], cC[64], ci[64], ct[64];
      const int zero = blockIdx.x >> 16;
      uint32_t h[56], yf[16];
      const uint32_t d0 = (sb & 0x3FFFF) >> 4;
      const uint32_t dK = d0 | (1u << 16), dN = d0 | (512u << 16);
      const uint32_t dX = dK + wg * 512;
      constexpr uint32_t RING = OFF_RING >> 4;
      auto waitA = [&](int n) { mbar_wait(bars + 8 * (B_FA + rslot(n)), rpar(n)); };
      auto freeA = [&](int n) { mbar_arrive_if(elect, bars + 8 * (B_EA + rslot(n))); };
      auto nop = [] {};

      asm volatile("bar.sync 0, 384;" ::: "memory");
#pragma unroll 1
      for (int i = 0; i < 4; i++) {
        const uint64_t dx = d128(dX + i * 2048), df = d128(dK + (OFF_XB >> 4) + (i & 1) * 1024);
        mbar_wait(bars + 8 * (B_FX + 2 * i), 0);
        wg_fence();
        mma_ss64<0, 0, 2>(cX, df, dx, i);
        mma_ss64<0, 0, 1>(cX, df + 2, dx + 2);
        wg_commit(); wg_wait<1>();
        mbar_arrive_if(elect && i, bars + 8 * (B_EA + rslot(i - 1)));
        mma_ss64<0, 0, 1>(cX, df + 4, dx + 4);
        mma_ss64<0, 0, 1>(cX, df + 6, dx + 6);
        if (i == 0 && tid == 0) PROF_EV(1);
        mbar_wait(bars + 8 * (B_FX + 2 * i + 1), 0);
        wg_fence();
#pragma unroll
        for (int k = 0; k < 4; k++) mma_ss64<0, 0, 1>(cX, df + (512 + k * 2), dx + (1024 + k * 2));
        wg_commit();
        waitA(i);
        wg_fence();
        const uint64_t da = d128(dX + i * 1024), db = d128(dN + RING + i * 1024);
        mma_ss128<0, 1, 2>(cA, da, db, i);
        wg_commit(); wg_wait<1>();
        mbar_arrive_if(elect, bars + 8 * (B_FE + i));
#pragma unroll
        for (int k = 1; k < 4; k++) mma_ss128<0, 1, 1>(cA, da + k * 2, db + k * 128);
        wg_commit();
      }
      fence_regs<0, 32>(cX);
#pragma unroll
      for (int e = 0; e < 16; e++) yf[e] = pack_pin(cX[2 * e], cX[2 * e + 1]);
      if (tid == 0) { PROF_EV(2); PROF_CK(42); }
      {
        waitA(4); mbar_wait(bars + 8 * B_E0, 0);
        const uint64_t de = d128(dN + (wg ? RING : OFF_XB >> 4));
        wg_fence();
        mma_rs128<0, 1, 0>(cB, yf[0], yf[1], yf[2], yf[3], de);
        wg_commit();
        wg_wait<1>();
        freeA(3);
#pragma unroll
        for (int k = 1; k < 4; k++) mma_rs128<0, 1, 1>(cB, yf[4 * k], yf[4 * k + 1], yf[4 * k + 2], yf[4 * k + 3], de + k * 128);
        wg_commit();
      }
      bool rel = false;
      auto acquire = [&](int n) {
        rel = elect;
        if (!mbar_try(bars + 8 * (B_FA + rslot(n)), rpar(n))) { wg_wait<0>(); freeA(n - 1); rel = false; waitA(n); }
      };
      auto freeP = [&](int n) { mbar_arrive_if(rel, bars + 8 * (B_EA + rslot(n - 1))); };
      auto ffn_step = [&](auto first, auto split, float (&acc)[64], int n, int kb, auto done, auto work) {
        constexpr int SPLIT = decltype(split)::value;
        acquire(n);
        wg_fence();
        const uint64_t dx = d128(dX + kb * 1024), db = d128(dN + RING + rslot(n) * 1024);
        mma_ss128<0, 1, decltype(first)::value>(acc, dx, db, kb);
#pragma unroll
        for (int k = 1; k < SPLIT; k++) mma_ss128<0, 1, 1>(acc, dx + k * 2, db + k * 128);
        wg_commit();
        work();
        wg_wait<1>();
        freeP(n);
        done();
        if (SPLIT < 4) {
          wg_fence();
#pragma unroll
          for (int k = SPLIT; k < 4; k++) mma_ss128<0, 1, 1>(acc, dx + k * 2, db + k * 128);
          wg_commit();
        }
      };
      {
        const int s0 = 2 * rb + wg, kr = 2 * ((s0 & 1) | ((s0 & 4) >> 1));
        const int m = lane >> 3, r = lane & 7;
        const uint32_t a0 = sb + OFF_XB + wg * 8192 + (((w >> 1) * 8 + (m >> 1)) * 2 + (w & 1)) * 256 + (m & 1) * 128 + ((r ^ (kr + (m & 1))) << 4);
        ffn_step(IC<1>(), IC<4>(), cA, 5, 4, [&] { fence_regs<0, 64>(cB); }, nop);
        asm volatile("bar.sync 5, 256;" ::: "memory");
        auto stage = [&](int i) {
          stsm4t(a0 + i * 1024, pack_bf16(cB[8 * i] - cB[34 + 8 * i], cB[8 * i + 1] - cB[35 + 8 * i]),
                 pack_bf16(cB[32 + 8 * i] + cB[8 * i + 2], cB[33 + 8 * i] + cB[8 * i + 3]),
                 pack_bf16(cB[8 * i + 4] - cB[38 + 8 * i], cB[8 * i + 5] - cB[39 + 8 * i]),
                 pack_bf16(cB[36 + 8 * i] + cB[8 * i + 6], cB[37 + 8 * i] + cB[8 * i + 7]));
          if (j == 0 && w == 0) {
            const uint32_t a1 = r ? sb + OFF_SP + 1024 : sb + OFF_SP + wg * 512 + (m & 1) * 256 + (m >> 1) * 128;
#pragma unroll
            for (int n = 2 * i; n < 2 * i + 2; n++)
              asm volatile("stmatrix.sync.aligned.m8n8.x4.shared.b16 [%0], {%1,%2,%3,%4};" ::"r"(a1 + ((n ^ (kr + (m >> 1)) ^ r) << 4)),
                           "r"(pack_bf16(cB[4 * n], cB[4 * n + 1])), "r"(pack_bf16(cB[4 * n + 2], cB[4 * n + 3])),
                           "r"(pack_bf16(cB[32 + 4 * n], cB[33 + 4 * n])), "r"(pack_bf16(cB[34 + 4 * n], cB[35 + 4 * n])) : "memory");
          }
        };
        auto publish = [&] {
          asm volatile("fence.proxy.async.shared::cta;" ::: "memory");
          __syncwarp();
          mbar_arrive_if(lane == 0, bars + 8 * (B_XS + wg));
          if (tid == 0) PROF_EV(3);
        };
        stage(0);
        ffn_step(IC<1>(), IC<1>(), cA, 6, 5, nop, nop);
        stage(1);
        ffn_step(IC<1>(), IC<1>(), cA, 7, 6, nop, nop);
        stage(2);
        ffn_step(IC<1>(), IC<2>(), cA, 8, 7, [&] { stage(3); }, nop);
        publish();
      }
      float g0 = 0.f, g1 = 0.f;
      uint32_t tag = 0;
      auto glu = [&](auto& acc, int half, int ho, int i0, int i1) {
#pragma unroll
        for (int i = i0; i < i1; i++) {
          const float o = 1.0f - ((i & 1) ? g1 : g0);
          asm volatile("" : "+f"(acc[2 * i]), "+f"(acc[2 * i + 1]), "+f"(acc[half + 2 * i]), "+f"(acc[half + 1 + 2 * i])::"memory");
          h[ho + i] = pack_pin(fmaxf(acc[2 * i], 0.f) * acc[half + 2 * i] * o, fmaxf(acc[2 * i + 1], 0.f) * acc[half + 1 + 2 * i] * o);
        }
      };
      ffn_step(IC<2>(), IC<1>(), cB, 9, zero, nop, nop);
#pragma unroll 1
      for (int kb = 1; kb < 8; kb++)
        ffn_step(IC<1>(), IC<1>(), cB, 9 + kb, kb, nop, [&] {
          if (kb == 4 + wg) {
            mbar_wait(bars + 8 * B_G, 0);
            const uint32_t gb0 = *(const uint32_t*)(smem + OFF_G + (wg * 64 + w * 16 + g) * 4), gb1 = *(const uint32_t*)(smem + OFF_G + (wg * 64 + w * 16 + g + 8) * 4);
            tag = gb0 & 1; g0 = __uint_as_float(gb0 & ~1u); g1 = __uint_as_float(gb1 & ~1u);
            glu(cA, 32, 0, 0, 8);
          } else if (kb == 6 + wg) glu(cA, 32, 0, 8, 16);
        });
      if (tid == 0) { PROF_EV(4); PROF_CK(43); }
      auto m_step = [&](auto first, int i) {
        acquire(17 + i);
        wg_fence();
        const uint64_t dx = d128(dX + i * 2048), dm = d64(dN + RING + rslot(17 + i) * 1024);
        mma_ss64<0, 1, decltype(first)::value>(ct, dx, dm);
#pragma unroll
        for (int k = 1; k < MSPLIT; k++) mma_ss64<0, 1, 1>(ct, dx + ((k >> 2) * 1024 + (k & 3) * 2), dm + k * 64);
        wg_commit();
        wg_wait<1>();
        freeP(17 + i);
        wg_fence();
#pragma unroll
        for (int k = MSPLIT; k < 8; k++) mma_ss64<0, 1, 1>(ct, dx + ((k >> 2) * 1024 + (k & 3) * 2), dm + k * 64);
        wg_commit();
      };
      m_step(IC<0>(), 0);
#pragma unroll 1
      for (int i = 1; i < 5; i++) {
        if (i == 1 + wg) glu(cB, 32, 16, 0, 8);
        else if (i == 3 + wg) glu(cB, 32, 16, 8, 16);
        if (i < 4) m_step(IC<1>(), i);
      }
      if (tid == 0) { PROF_EV(5); PROF_CK(44); }
      ffn_step(IC<0>(), IC<1>(), cC, 21, 0, nop, nop);
#pragma unroll 1
      for (int kb = 1; kb < 8; kb++)
        ffn_step(IC<1>(), IC<1>(), cC, 21 + kb, kb, [&] { mbar_arrive_if(elect && !(kb & 1), bars + 8 * (B_ET + (kb >> 1) - 1)); }, [&] {
          if (kb == 1 + wg) glu(ct, 16, 48, 0, 8);
        });

      auto twait = [&](uint32_t bar, uint32_t par, int) { mbar_wait(bar, par); };
      auto tr = [] {};
      const int fo = warp * 128 + lane;
      auto fetch = [&](uint4 (&pv)[4], int z) {
        twait(bars + 8 * (z < 4 ? B_Z + 2 * z + wg : B_HP + z - 4), 0, 8 + z);
        const uint8_t* src = smem + (z < 5 ? OFF_Z + z * U : (z - 5) * U) + fo * 16;
#pragma unroll
        for (int i = 0; i < 4; i++) pv[i] = *(const uint4*)(src + i * 512);
      };
      auto check = [&](uint4 (&pv)[4], int z) {
        const uint32_t t0 = (uint32_t)clock();
        while (__any_sync(0xffffffffu, ((pv[0].x ^ tag) | (pv[1].x ^ tag) | (pv[2].x ^ tag) | (pv[3].x ^ tag)) & 1)) {
#pragma unroll
          for (int i = 0; i < 4; i++) pv[i] = ld_x4(ws->part + (size_t)((rb * 8 + j) * 3 + z - 4) * 1024 + fo + i * 32);
          spin_guard(t0);
        }
#pragma unroll
        for (int i = 0; i < 4; i++) pv[i].x &= ~1u;
      };
      const uint32_t peerZ = mapa(sb + OFF_Z + fo * 16, rank ^ 1), peerB = mapa(bars + 8 * (B_Z + wg), rank ^ 1);
      auto tile_mma = [&](auto off, int t, int k0, int k1, int init) {
        constexpr int O = decltype(off)::value;
        const uint64_t db = d128(dN + (t & 3) * (TB >> 4)), dw = db + rank * 256, dm = db + (rank ? 0 : 1536);
#pragma unroll
        for (int k = k0; k < k1; k++) {
          if (k == 0) mma_rs64<O, 1, 2>(ct, h[0], h[1], h[2], h[3], dw, init);
          else if (k < 14) mma_rs64<O, 1, 1>(ct, h[4 * k], h[4 * k + 1], h[4 * k + 2], h[4 * k + 3], k < 12 ? dw + k * 128 : dm + (k - 12) * 128);
          else mma_rs64<O, 1, 1>(ct, yf[4 * k - 56], yf[4 * k - 55], yf[4 * k - 54], yf[4 * k - 53], db + k * 128);
        }
      };
      auto tile = [&](auto off, int t) {
        constexpr int P = 32 - decltype(off)::value;
        const bool grid = t >= 4 && t < 7, pre = t != 1 && t != 5;
        const int zo = grid ? t - 4 : t == 7 ? 3 : t - 1, z = t - 2;
        const int owner = rb * 8 + 2 * ((q4 + zo + 1) & 3) + rank;
        uint4* dst = ws->part + (size_t)(owner * 3 + zo) * 1024 + fo;
        const uint32_t src = sb + (z < 5 ? OFF_Z + z * U : (z - 5) * U) + fo * 16;
        twait(bars + 8 * (B_FT + (t & 3)), t >> 2, t);
        wg_fence();
        tile_mma(off, t, 0, TH, t >= 3 && t != 6);
        wg_commit();
        wg_wait<1>();
        mbar_arrive_if(elect && t < 6, bars + 8 * (B_ET + t - 1));
        if (t == 1) twait(bars + 8 * B_RDY, 0, 15);
        fence_regs<P, 32>(ct);
        uint32_t pk[16];
#pragma unroll
        for (int i = 0; i < 16; i++) pk[i] = pack_bf16(ct[P + 2 * i], ct[P + 2 * i + 1]);
        wg_fence();
#pragma unroll
        for (int i = 0; i < 4; i++) {
          asm volatile(
              "{\n.reg .pred p;\nsetp.ne.b32 p, %7, 0;\n@p st.relaxed.gpu.global.v4.u32 [%0], {%3,%4,%5,%6};\n"
              "@!p st.async.weak.shared::cluster.mbarrier::complete_tx::bytes.v4.b32 [%1], {%3,%4,%5,%6}, [%2];\n}" ::"l"(dst + i * 32),
              "r"(peerZ + zo * U + i * 512), "r"(peerB + 16 * zo), "r"((pk[4 * i] & ~(uint32_t)grid) | (tag & grid)), "r"(pk[4 * i + 1]), "r"(pk[4 * i + 2]),
              "r"(pk[4 * i + 3]), "r"((int)grid) : "memory");
          if (i == 3) hint_add_if(grid && lane == 0, &ws->cntP[32 * owner + zo]);
          tile_mma(off, t, TH + 2 * i, TH + 2 * i + 2, 0);
        }
        wg_commit();
        if (pre) twait(bars + 8 * (z < 4 ? B_Z + 2 * z + wg : B_HP + z - 4), 0, 8 + z);
        wg_fence();
        uint4 pv[4];
#pragma unroll
        for (int i = 0; i < 4; i++) {
          asm volatile("{\n.reg .pred p;\nsetp.ne.b32 p, %5, 0;\n@p ld.shared.v4.u32 {%0,%1,%2,%3}, [%4];\n}"
                       : "=r"(pv[i].x), "=r"(pv[i].y), "=r"(pv[i].z), "=r"(pv[i].w) : "r"(src + i * 512), "r"((int)pre) : "memory");
          tile_mma(off, t, TH + 8 + i, i < 3 ? TH + 9 + i : 18, 0);
        }
        wg_commit();
        if (pre) {
          if (z >= 4) check(pv, z);
#pragma unroll
          for (int i = 0; i < 4; i++) {
            const uint32_t a[4] = {pv[i].x, pv[i].y, pv[i].z, pv[i].w};
#pragma unroll
            for (int e = 0; e < 4; e++) { ct[P + 8 * i + 2 * e] = bf_lo(a[e]); ct[P + 8 * i + 2 * e + 1] = bf_hi(a[e]); }
          }
        }
      };
      asm volatile("barrier.cluster.wait.aligned;" ::: "memory");
      twait(bars + 8 * B_FT, 0, 0);
      wg_fence();
      tile_mma(IC<0>(), 0, 0, 5, zero);
      wg_commit();
      wg_wait<1>();
      mbar_arrive_if(elect, bars + 8 * (B_ET + 3));
      glu(cC, 32, 32, 0, 8);
      waitA(29 + wg);
      wg_fence();
      tile_mma(IC<0>(), 0, 5, 8, 0);
      tile_mma(IC<0>(), 0, 12, 14, 0);
      wg_commit();
      glu(cC, 32, 32, 8, 16);
      if (tid == 0) PROF_EV(6);
      if (tid == 128) PROF_EV(27);
      mbar_wait(bars + 8 * (j == 0 ? B_T : B_TL), 0);
      if (tid == 0) { PROF_EV(7); PROF_CK(45); }
      wg_fence();
      {
        const uint64_t dt = d128(dN + (OFF_T >> 4) + wg * 512), de = d128(dK + RING + (1 + wg) * 1024);
        mma_ss64<0, 1, 0>(ci, de, dt);
        mma_ss64<32, 1, 0>(ci, de + 512, dt);
#pragma unroll
        for (int k = 1; k < 4; k++) {
          mma_ss64<0, 1, 1>(ci, de + k * 2, dt + k * 128);
          mma_ss64<32, 1, 1>(ci, de + (512 + k * 2), dt + k * 128);
        }
        wg_commit();
      }
      tile_mma(IC<0>(), 0, 8, 12, 0);
      wg_commit();
      wg_wait<1>();
      if (elect) asm volatile("mbarrier.arrive.shared::cluster.b64 _, [%0];" ::"r"(mapa(bars + 8 * B_RDY, rank ^ 1)) : "memory");
      mbar_arrive_if(elect, bars + 8 * (B_PZ + 1));
      fence_regs<0, 64>(ci);
#pragma unroll
      for (int i = 0; i < 16; i++) {
        const float gg = ((i & 1) ? g1 : g0) * (2.0f / (2048.0f * 512.0f));
        if (i & 2) yf[i] = pack_pin((ci[2 * i] - ci[28 + 2 * i]) * gg, (ci[2 * i + 1] - ci[29 + 2 * i]) * gg);
        else yf[i] = pack_pin((ci[2 * i] + ci[36 + 2 * i]) * gg, (ci[2 * i + 1] + ci[37 + 2 * i]) * gg);
      }
      wg_fence();
      tile_mma(IC<0>(), 0, 14, 18, 0);
      wg_commit();
      if (tid == 0) PROF_EV(8);
      if (tid == 128) PROF_EV(28);
#pragma unroll 1
      for (int t = 1;; t += 2) {
        tile(IC<32>(), t);
        if (t == 7) break;
        tile(IC<0>(), t + 1);
      }
      if (tid == 0) { PROF_EV(9); PROF_CK(46); }
      if (tid == 128) PROF_EV(29);
      {
        float (&sum)[64] = ct;
        uint4 p2[4], p3[4];
        fetch(p3, 3);
        if (tid == 0) PROF_EV(25);
        fetch(p2, 6);
        if (tid == 0) PROF_EV(24);
        check(p2, 6);
#pragma unroll
        for (int i = 0; i < 4; i++) {
          const uint32_t b[4] = {p2[i].x, p2[i].y, p2[i].z, p2[i].w}, c[4] = {p3[i].x, p3[i].y, p3[i].z, p3[i].w};
#pragma unroll
          for (int e = 0; e < 4; e++) {
            sum[8 * i + 2 * e] += bf_lo(c[e]) + bf_lo(b[e]);
            sum[8 * i + 2 * e + 1] += bf_hi(c[e]) + bf_hi(b[e]);
          }
        }
        if (tid == 0) PROF_EV(14);
        wg_wait<0>();
        fence_regs<32, 32>(ct);
#pragma unroll
        for (int i = 0; i < 32; i++) sum[i] += ct[32 + i];
        const uint32_t stg = sb + OFF_T + warp * 2048;
        const int mr = (lane & 7) + ((lane >> 3) & 1) * 8, mc = lane >> 4;
#pragma unroll
        for (int i = 0; i < 4; i++) {
          const uint32_t a = stg + mr * 128 + (((2 * i + mc) ^ (mr & 7)) << 4);
          asm volatile("stmatrix.sync.aligned.m8n8.x4.shared.b16 [%0], {%1,%2,%3,%4};" ::"r"(a), "r"(pack_bf16(sum[8 * i], sum[8 * i + 1])),
                       "r"(pack_bf16(sum[8 * i + 2], sum[8 * i + 3])), "r"(pack_bf16(sum[8 * i + 4], sum[8 * i + 5])),
                       "r"(pack_bf16(sum[8 * i + 6], sum[8 * i + 7])) : "memory");
        }
        asm volatile("fence.proxy.async.shared::cta;" ::: "memory");
        __syncwarp();
        if (elect_one()) {
          asm volatile("cp.async.bulk.tensor.3d.global.shared::cta.bulk_group [%0, {%2, %3, %4}], [%1];" ::"l"(&maps.o), "r"(stg), "r"(64 * j),
                       "r"(16 * w), "r"(2 * rb + wg) : "memory");
          asm volatile("cp.async.bulk.commit_group;\ncp.async.bulk.wait_group.read 0;" ::: "memory");
        }
      }
      if (tid == 0) { PROF_EV(15); PROF_CK(41); }
      if (tid == 128) PROF_EV(30);
    }
  } else if (warp < 12) {
    asm volatile("setmaxnreg.dec.sync.aligned.u32 104;");
    asm volatile("barrier.cluster.arrive.relaxed.aligned;" ::: "memory");
    const int t = tid - 256, w = warp - 8;
    const uint32_t ep = ld_x1(&ws->epoch[blockIdx.x * 8]);
    const uint32_t tag = (ep + 1) & 1;
    auto w_issue = [&](const CUtensorMap* m) {
          if (elect_one()) { mbar_expect_tx(bars + 8 * (B_WR + w), 3072); tma4d(sb + OFF_T + w * 3072, m, bars + 8 * (B_WR + w), 16 * kg, 0, 2 * w, tn); }
          __syncwarp();
    };
    auto gate_rows = [&] {
      const int r = 16 * j + 4 * w + (lane >> 3);
      const uint4* pg = (const uint4*)gate_w + (lane & 7);
      {
        float a = 0.f;
        asm volatile("bar.sync 4, 256;" ::: "memory");
#pragma unroll 1
        for (int hf = 0; hf < 2; hf++) {
          uint4 v[4], u[4];
#pragma unroll
          for (int kb = 0; kb < 4; kb++) v[kb] = __ldg(pg + (4 * hf + kb) * 8);
          mbar_wait(bars + 8 * (B_FE + 1 + 2 * hf), 0);
          if (hf) w_issue(&maps.wr);
#pragma unroll
          for (int kb = 0; kb < 4; kb++) u[kb] = *(const uint4*)(smem + (4 * hf + kb) * U + r * 128 + (((lane ^ r) & 7) << 4));
#pragma unroll
          for (int kb = 0; kb < 4; kb++) {
            a = fmaf(bf_lo(u[kb].x), bf_lo(v[kb].x), a); a = fmaf(bf_hi(u[kb].x), bf_hi(v[kb].x), a);
            a = fmaf(bf_lo(u[kb].y), bf_lo(v[kb].y), a); a = fmaf(bf_hi(u[kb].y), bf_hi(v[kb].y), a);
            a = fmaf(bf_lo(u[kb].z), bf_lo(v[kb].z), a); a = fmaf(bf_hi(u[kb].z), bf_hi(v[kb].z), a);
            a = fmaf(bf_lo(u[kb].w), bf_lo(v[kb].w), a); a = fmaf(bf_hi(u[kb].w), bf_hi(v[kb].w), a);
          }
        }
#pragma unroll
        for (int o = 4; o; o >>= 1) a += __shfl_xor_sync(0xffffffffu, a, o);
        if ((lane & 7) == 0)
          asm volatile("st.relaxed.gpu.global.f32 [%0], %1;" ::"l"(ws->gate + rb * 128 + r), "f"(tagf(__fdividef(1.0f, 1.0f + __expf(-a)), tag)) : "memory");
        if (t == 0) PROF_EV(18);
      }
    };
    {
      const int g = lane >> 2, q = lane & 3;
      uint32_t wf[32];
      if (!helper) {
        gate_rows();
        const uint32_t wa = sb + OFF_T + w * (3072 + 4) + q * 48 + g * 2;
#pragma unroll 1
        for (int ri = 0; ri < 2; ri++) {
          mbar_wait(bars + 8 * (B_WR + w), ri);
#pragma unroll
          for (int n2 = 0; n2 < 32 / WB; n2++) {
            uint32_t v[WB];
#pragma unroll
            for (int i = 0; i < WB; i++) {
              const int e = n2 * WB + i;
              asm volatile("ld.shared.u16 %0, [%1];" : "=r"(v[i]) : "r"(wa + ((e >> 1) & 7) * 192 + (e & 1) * (1536 + 2) + (e >> 4) * 16) : "memory");
            }
#pragma unroll
            for (int i = 0; i < WB; i++) wf[n2 * WB + i] = __byte_perm(wf[n2 * WB + i], v[i], 0x5432);
            if (WSLEEP) { asm volatile("nanosleep.u32 %0;" ::"r"(WSLEEP + (v[WB - 1] >> 16)) : "memory"); }
          }
          __syncwarp();
          if (ri == 0) w_issue(&maps.wi);
        }
        asm volatile("bar.sync 1, 128;" ::: "memory");
        if (t == 0) PROF_EV(11);
      } else {
        asm volatile("bar.sync 4, 256;" ::: "memory");
        hint_wait(&ws->cntW[0], (ep + 1) * 128u);
        const uint32_t t0 = (uint32_t)clock();
#pragma unroll 1
        for (;;) {
          uint32_t bad = 0;
#pragma unroll
          for (int i = 0; i < 32; i++) {
            const float2 v = ld_x2((const float2*)ws->Wh + (i >> 4) * 2048 + 16 * w + g + 8 * (i & 1) + 64 * q + ((i >> 1) & 7) * 256);
            wf[i] = __float_as_uint(v.x); bad |= __float_as_uint(v.y) ^ tag;
          }
          if (!__any_sync(0xffffffffu, bad & 1)) break;
          spin_guard(t0);
        }
        if (t == 0) PROF_EV(11);
      }
      if (w == 0 && elect_one()) { mbar_expect_tx(bars + 8 * B_W, 8192); bulk_load(sb + OFF_D, dtab, 8192, bars + 8 * B_W); }
      mbar_wait(bars + 8 * B_W, 0);
      mbar_wait(bars + 8 * B_HX, 0);
      if (t == 0) PROF_EV(12);
      const uint32_t dd = (sb & 0x3FFFF) >> 4;
      const uint64_t dF = d128((dd + (OFF_D >> 4)) | (512u << 16)), dI = d128((dd + (OFF_D >> 4)) | (1u << 16)), dA = d128((dd + (OFF_XB >> 4)) | (512u << 16));
      float az[32];
      const int zero = blockIdx.x >> 16;
      uint32_t pf[32];
#pragma unroll
      for (int mt = 0; mt < 2; mt++) {
        wg_fence();
        if (mt == 0) mma_ss64<0, 3, 0>(az, dA, dF);
        else mma_ss64<0, 3, 2>(az, dA + 512, dF, zero);
#pragma unroll
        for (int k = 1; k < 4; k++) mma_ss64<0, 3, 1>(az, dA + (mt * 512 + k * 128), dF + k * 128);
        wg_commit();
        wg_wait<0>();
        fence_regs<0, 32>(az);
#pragma unroll
        for (int i = 0; i < 16; i++) {
          const float wr = bf_lo(wf[16 * mt + i]), wi = bf_hi(wf[16 * mt + i]);
          pf[16 * mt + i] = pack_pin(fmaf(az[2 * i], wr, -az[2 * i + 1] * wi), fmaf(az[2 * i], wi, az[2 * i + 1] * wr));
        }
      }
      if (t == 0) PROF_EV(16);
      {
        const int m = lane >> 3, r = lane & 7;
        const int sl = 2 * (m >> 1) + ((r >> 1) & 1) + 4 * (r >> 2);
        const uint32_t a0 = sb + OFF_XB + (2 * w + (m & 1)) * 2048 + sl * 64;
        uint32_t pk[16];
#pragma unroll
        for (int mt = 0; mt < 3; mt++) {
          if (mt < 2) {
            wg_fence();
            mma_rs64<0, 0, 2>(az, pf[16 * mt], pf[16 * mt + 1], pf[16 * mt + 2], pf[16 * mt + 3], dI, mt ? (int)helper : zero);
#pragma unroll
            for (int k = 1; k < 4; k++) mma_rs64<0, 0, 1>(az, pf[16 * mt + 4 * k], pf[16 * mt + 4 * k + 1], pf[16 * mt + 4 * k + 2], pf[16 * mt + 4 * k + 3], dI + k * 2);
            wg_commit();
          }
          if (mt > 0 && !helper) {
#pragma unroll
            for (int i = 0; i < 4; i++) stsm4t(a0 + ((((mt - 1) * 2 + (r & 1)) ^ (sl >> 1)) << 4) + i * 512, pk[4 * i], pk[4 * i + 1], pk[4 * i + 2], pk[4 * i + 3]);
          }
          if (mt < 2) {
            wg_wait<0>();
            fence_regs<0, 32>(az);
#pragma unroll
            for (int i = 0; i < 16; i++) pk[i] = pack_pin(az[2 * i], az[2 * i + 1]);
          }
        }
      }
      if (helper) {
#pragma unroll
        for (int i = 0; i < 16; i++) {
          const int n = i >> 1, s0 = 8 * (n >> 1) + 2 * (n & 1) + (q & 1) + 4 * (q >> 1);
          if ((n & 1) == (int)(blockIdx.x & 1)) st_u2(ws->Ts + s0 * 64 + 16 * w + g + 8 * (i & 1), pack_bf16(az[2 * i], az[2 * i + 1]), tag);
        }
        __syncwarp();
        hint_add_if(lane == 0, &ws->cntH[0]);
        if (t == 0) { ws->epoch[blockIdx.x * 8] = ep + 1; PROF_EV(13); }
      } else {
        asm volatile("fence.proxy.async.shared::cta;" ::: "memory");
        __syncwarp();
        if (elect_one()) {
          if (t == 0) PROF_EV(17);
          if (SPACE) __nanosleep(SPACE * w);
          asm volatile("cp.async.bulk.tensor.3d.global.shared::cta.bulk_group [%0, {%2, %3, %4}], [%1];" ::"l"(&maps.ts), "r"(sb + OFF_XB + w * 4096),
                       "r"(32 * kg), "r"(0), "r"(8 * tn + 2 * w) : "memory");
          bulk_done_signal(&ws->cntT[32 * j]);
          if (t == 96) PROF_EV(13);
        }
        __syncwarp();
        if (j == 0) {
          hint_wait(&ws->cntH[0], (ep + 1) * 8u);
          const uint32_t t0 = (uint32_t)clock();
          float2 v;
          do { v = ld_x2((const float2*)ws->Ts + 2 * rb * 64 + t); spin_guard(t0); } while (__any_sync(0xffffffffu, (__float_as_uint(v.y) ^ tag) & 1));
          mbar_wait(bars + 8 * B_TL, 0);
          const uint32_t u = __float_as_uint(v.x);
          *(uint16_t*)(smem + OFF_T + t * 128 + ((t & 7) << 4)) = (uint16_t)u;
          *(uint16_t*)(smem + OFF_T + t * 128 + (((t & 7) ^ 1) << 4)) = (uint16_t)(u >> 16);
          asm volatile("fence.proxy.async.shared::cta;" ::: "memory");
          __syncwarp();
          mbar_arrive_if(lane == 0, bars + 8 * B_T);
        }
      }
    }
  } else {
    asm volatile("setmaxnreg.dec.sync.aligned.u32 24;");
    auto xf_load = [&](int q) {
      const uint32_t fb = bars + 8 * (B_FX + q);
      mbar_expect_tx(fb, U + 8192);
      tma3d(sb + q * U, &maps.x, fb, 64 * q, 0, 2 * rb);
      if (q >= 4) mbar_wait(bars + 8 * (B_FE + ((q - 4) >> 1)), 0);
      tma2d(sb + OFF_XB + (q & 3) * 8192, &maps.ft, fb, 64 * q, 64 * j);
    };
    if (elect_one()) {
      if (warp == 14) {
#pragma unroll
        for (int i = 0; i < B_FT; i++) mbar_init(bars + 8 * i, 1);
        asm volatile("fence.mbarrier_init.release.cluster;" ::: "memory");
        if (!helper) {
#pragma unroll 1
          for (int n = 0; n < 2; n++) {
            const uint32_t fb = bars + 8 * (B_FA + n);
            xf_load(2 * n); xf_load(2 * n + 1);
            mbar_expect_tx(fb, U);
            tma2d(sb + OFF_RING + n * U, &maps.g64, fb, f_full, 64 * n);
            tma2d(sb + OFF_RING + n * U + 8192, &maps.u64, fb, f_full, 64 * n);
          }
        }
      } else if (warp == 15) {
#pragma unroll
        for (int i = B_FT; i < NBAR; i++) mbar_init(bars + 8 * i, i < B_EA ? 1 : i < B_T ? 2 : 4);
#pragma unroll
        for (int i = 0; i < 8; i++) mbar_expect_tx(bars + 8 * (B_Z + i), U / 2);
        asm volatile("fence.mbarrier_init.release.cluster;" ::: "memory");
        asm volatile("fence.proxy.async.shared::cta;" ::: "memory");
      } else if (warp == 13 && !PF0) {
#pragma unroll
        for (int i = 1; i < 4; i++) asm volatile("prefetch.tensormap [%0];" ::"l"((const char*)&maps + i * 128) : "memory");
      }
    }
    __syncwarp();
    asm volatile("bar.arrive 0, 384;" ::: "memory");
    asm volatile("bar.arrive 4, 256;" ::: "memory");
    __syncwarp();
    asm volatile("barrier.cluster.arrive.relaxed.aligned;" ::: "memory");
    asm volatile("bar.sync 3, 128;" ::: "memory");
    if (warp == 15 && !helper) {
        mbar_wait(bars + 8 * B_FE, 0);
        const uint32_t tag = (ld_x1(&ws->epoch[blockIdx.x * 8]) + 1) & 1;
        const int c = lane >> 4, jj = 16 * blockIdx.x + (lane & 15), jm = (2048 - jj) & 2047;
        const unsigned short* pr = (const unsigned short*)w_r + 256 * c;
        const unsigned short* pi = (const unsigned short*)w_i + 256 * c;
        const float wr = 0.25f * (bf_lo(__ldg(pr + jj * 257)) + bf_lo(__ldg(pr + jm * 257)));
        const float wi = 0.25f * (bf_lo(__ldg(pi + jj * 257)) - bf_lo(__ldg(pi + jm * 257)));
        st_u2(ws->Wh + c * 2048 + jj, c ? pack_bf16(-wi, wr) : pack_bf16(wr, wi), tag);
        __syncwarp();
        hint_add_if(lane == 0, &ws->cntW[0]);
        mbar_wait(bars + 8 * B_XS, 0);
        const uint32_t t0 = (uint32_t)clock();
        uint4 v;
        do { v = ld_x4(ws->gate + rb * 128 + 4 * lane); spin_guard(t0); } while (__any_sync(0xffffffffu, ((v.x ^ tag) | (v.y ^ tag) | (v.z ^ tag) | (v.w ^ tag)) & 1));
        *(uint4*)(smem + OFF_G + lane * 16) = v;
        __syncwarp();
        mbar_arrive_if(lane < 4, bars + 8 * B_G);
      }
    if ((!helper || warp == 15) && elect_one()) {
      if (warp < 14) {
        const int p = warp - 12;
#pragma unroll 1
        for (int i = 4 + p; i < 14; i += 2) asm volatile("prefetch.tensormap [%0];" ::"l"((const char*)&maps + i * 128) : "memory");
#pragma unroll 1
        for (int n = 2; n < 31; n++) {
          const bool table = n == 4 || n >= 29;
          const bool half = n >= 17 && n < 21;
          const int q = n < 4 ? n : n < 17 ? n - 1 : n - 5;
          const CUtensorMap* m = table ? &maps.e : half ? &maps.g32 + p : &maps.g64 + p;
          const int c0 = table ? 0 : half ? f_half : f_full + 64 * (q >> 3);
          const int c1 = table ? (2 * rb + ((n & 1) ^ 1)) * 128 + 64 * p : half ? 128 * (n - 17) : 64 * (q & 7);
          const uint32_t fb = bars + 8 * (B_FA + (n & 3)), dst = sb + OFF_RING + (n & 3) * U + p * 8192;
          if (n < 4) mbar_wait(bars + 8 * (B_FE + n - 2), 0);
          else mbar_wait(bars + 8 * (B_EA + (n & 3)), ((n >> 2) & 1) ^ 1);
          tma2d(dst, m, fb, c0, c1);
          if (p == 0) mbar_expect_tx(fb, U);
        }
      } else if (warp == 15) {
        const unsigned ep1 = ld_x1(&ws->epoch[blockIdx.x * 8]) + 1;
        flag_wait(&ws->cntX[helper ? 0 : 32 * j], ep1 * 16u);
        PROF_EV(22);
        mbar_expect_tx(bars + 8 * B_HX, U);
        bulk_load(sb + OFF_XB, ws->X + (size_t)(helper ? 128 : kg * 8 + tn) * 8192, U, bars + 8 * B_HX);
        if (!helper) {
          flag_wait(&ws->cntT[32 * j], ep1 * 64u);
          PROF_EV(23);
          mbar_expect_tx(bars + 8 * B_TL, U);
          tma3d(sb + OFF_T, &maps.t, bars + 8 * B_TL, 64 * j, 0, 2 * rb);
#pragma unroll 1
          for (int i = 0; i < 3; i++) {
            flag_wait(&ws->cntP[32 * (rb * 8 + j) + i], ep1 * 8u);
            mbar_wait(bars + 8 * (B_PZ + (i == 0)), 0);
            if (i == 2) PROF_EV(26);
            mbar_expect_tx(bars + 8 * (B_HP + i), U);
            bulk_load(sb + (i ? (i - 1) * U : OFF_T), ws->part + (size_t)((rb * 8 + j) * 3 + i) * 1024, U, bars + 8 * (B_HP + i));
          }
          ws->epoch[blockIdx.x * 8] = ep1;
        }
      } else {
#pragma unroll 1
        for (int q = 4; q < 8; q++) xf_load(q);
        mbar_wait(bars + 8 * (B_FE + 2), 0);
        mbar_expect_tx(bars + 8 * B_E0, U);
        tma2d(sb + OFF_XB, &maps.e, bars + 8 * B_E0, 0, 2 * rb * 128);
        tma2d(sb + OFF_XB + 8192, &maps.e, bars + 8 * B_E0, 0, 2 * rb * 128 + 64);
#pragma unroll 1
        for (int h2 = 0; h2 < 2; h2++) {
          const int s0 = 2 * rb + h2, sg = (s0 & ~6) | ((s0 & 2) << 1) | ((s0 & 4) >> 1);
          mbar_wait(bars + 8 * (B_XS + h2), 0);
#pragma unroll 1
          for (int c = 0; c < 2; c++) {
            asm volatile("cp.async.bulk.tensor.4d.global.shared::cta.bulk_group [%0, {%2, %3, %4, %5}], [%1];" ::"l"(&maps.xs),
                         "r"(sb + OFF_XB + h2 * 8192 + c * 4096), "r"(0), "r"(sg), "r"(0), "r"(16 * j + 8 * c) : "memory");
            if (j == 0)
              asm volatile("cp.async.bulk.global.shared::cta.bulk_group [%0], [%1], 256;" ::"l"(ws->X + 128 * 8192 + c * 4096 + sg * 128),
                           "r"(sb + OFF_SP + h2 * 512 + c * 256) : "memory");
            if (SPACE && h2 + c < 2) __nanosleep(SPACE);
          }
        }
        bulk_done_signal(&ws->cntX[32 * j]);
        PROF_EV(20);
        if (rb < 8) asm volatile("cp.async.bulk.prefetch.tensor.2d.L2.global [%0, {%1, %2}];" ::"l"(&maps.g32 + (rb >> 2)), "r"(f_half), "r"(128 * (rb & 3)) : "memory");
        else asm volatile("cp.async.bulk.prefetch.tensor.2d.L2.global [%0, {%1, %2}];" ::"l"(&maps.d224), "r"(64 * (rb - 8)), "r"(224 * j) : "memory");
#pragma unroll 1
        for (int t = 0; t < 8; t++) {
          const int i = t < 3 ? t + 1 : t < 6 ? t - 2 : 0;
          const int col = 64 * (2 * ((q4 + i) & 3) + ((t < 3 || t == 6) ? 1 - rank : rank));
          const uint32_t fb = bars + 8 * (B_FT + (t & 3)), dst = sb + (t & 3) * TB;
          mbar_wait(bars + 8 * (B_ET + (t == 2 ? 3 : t & 3)), t >> 2);
          mbar_expect_tx(fb, TB);
          tma2d(dst, &maps.d224, fb, col, 224 * j);
          if (t < 2) mbar_wait(bars + 8 * (B_ET + t + 1), 0);
          tma2d(dst + 28672, &maps.ft, fb, col, 64 * j);
        }
      }
    }
  }
}

typedef CUresult (*EncodeFn)(CUtensorMap*, CUtensorMapDataType, cuuint32_t, void*, const cuuint64_t*, const cuuint64_t*, const cuuint32_t*,
                             const cuuint32_t*, CUtensorMapInterleave, CUtensorMapSwizzle, CUtensorMapL2promotion, CUtensorMapFloatOOBfill);

static void encode(EncodeFn f, CUtensorMap* m, const void* base, int rank, const cuuint64_t* dims, const cuuint64_t* strides, const cuuint32_t* box,
                   CUtensorMapSwizzle sw) {
  cuuint32_t es[5] = {1, 1, 1, 1, 1};
  f(m, CU_TENSOR_MAP_DATA_TYPE_BFLOAT16, rank, (void*)base, dims, strides, box, es, CU_TENSOR_MAP_INTERLEAVE_NONE, sw,
    CU_TENSOR_MAP_L2_PROMOTION_L2_128B, CU_TENSOR_MAP_FLOAT_OOB_FILL_NONE);
}

extern "C" void kernel_launch(void* const* d_in, const int* in_sizes, int n_in, void* d_out, int out_size) {
  (void)in_sizes; (void)n_in; (void)out_size;
  const __nv_bfloat16* x = (const __nv_bfloat16*)d_in[0];
  const __nv_bfloat16* w_r = (const __nv_bfloat16*)d_in[1];
  const __nv_bfloat16* w_i = (const __nv_bfloat16*)d_in[2];
  const __nv_bfloat16* Wg = (const __nv_bfloat16*)d_in[4];
  const __nv_bfloat16* Wu = (const __nv_bfloat16*)d_in[5];
  const __nv_bfloat16* Wd = (const __nv_bfloat16*)d_in[6];
  const __nv_bfloat16* gw = (const __nv_bfloat16*)d_in[7];

  void* fp = nullptr; cudaDriverEntryPointQueryResult qr;
  cudaGetDriverEntryPoint("cuTensorMapEncodeTiled", &fp, cudaEnableDefault, &qr);
  EncodeFn enc = (EncodeFn)fp;
  void *pFT, *pET, *pDT, *pW;
  cudaGetSymbolAddress(&pDT, g_DT); cudaGetSymbolAddress(&pW, g_work);
  void *pX = ((Work*)pW)->X, *pT = ((Work*)pW)->T;
  cudaGetSymbolAddress(&pFT, g_FT); cudaGetSymbolAddress(&pET, g_ET);

  Maps mp;
  const CUtensorMapSwizzle S128 = CU_TENSOR_MAP_SWIZZLE_128B, S64 = CU_TENSOR_MAP_SWIZZLE_64B;
  { cuuint64_t d[3] = {512, 64, 32}, s[2] = {32768, 1024}; cuuint32_t b[3] = {64, 64, 2}, b2[3] = {64, 16, 1};
    encode(enc, &mp.x, x, 3, d, s, b, S128); encode(enc, &mp.o, d_out, 3, d, s, b2, S128); }
  { cuuint64_t d[2] = {512, 512}, s[1] = {1024}; cuuint32_t b[2] = {64, 64}; encode(enc, &mp.ft, pFT, 2, d, s, b, S128); }
  { cuuint64_t d[4] = {128, 32, 2, 129}, s[3] = {256, 8192, 16384}; cuuint32_t b[4] = {128, 1, 2, 8}; encode(enc, &mp.xs, pX, 4, d, s, b, CU_TENSOR_MAP_SWIZZLE_NONE); }
  { cuuint64_t d[3] = {512, 32, 64}, s[2] = {65536, 1024}; cuuint32_t b[3] = {32, 32, 2}; encode(enc, &mp.ts, pT, 3, d, s, b, S64); }
  { cuuint64_t d[3] = {512, 64, 32}, s[2] = {1024, 65536}; cuuint32_t b[3] = {64, 64, 2}; encode(enc, &mp.t, pT, 3, d, s, b, S128); }
  { cuuint64_t d[2] = {64, 4096}, s[1] = {128}; cuuint32_t b[2] = {64, 64}; encode(enc, &mp.e, pET, 2, d, s, b, S128); }
  { cuuint64_t d[2] = {1792, 512}, s[1] = {3584}; cuuint32_t b[2] = {64, 64}, b2[2] = {32, 128};
    encode(enc, &mp.g64, Wg, 2, d, s, b, S128); encode(enc, &mp.u64, Wu, 2, d, s, b, S128);
    encode(enc, &mp.g32, Wg, 2, d, s, b2, S64); encode(enc, &mp.u32, Wu, 2, d, s, b2, S64); }
  { cuuint64_t d[2] = {512, 1792}, s[1] = {1024}; cuuint32_t b[2] = {64, 224}; encode(enc, &mp.d224, Wd, 2, d, s, b, S128); }
  { cuuint64_t d[4] = {264, 32, 8, 8}, s[3] = {32896, 512, 4112}; cuuint32_t b[4] = {24, 32, 2, 1};
    encode(enc, &mp.wr, w_r, 4, d, s, b, CU_TENSOR_MAP_SWIZZLE_NONE); encode(enc, &mp.wi, w_i, 4, d, s, b, CU_TENSOR_MAP_SWIZZLE_NONE); }

  cudaFuncSetAttribute(fused_kernel, cudaFuncAttributeMaxDynamicSharedMemorySize, SMEM_BYTES);
  fused_kernel<<<NCTA, 512, SMEM_BYTES>>>((Work*)pW, (const uint16_t*)pDT, w_r, w_i, gw, x, (const uint16_t*)pFT, Wg, Wu, mp);
}
```

```cpp
#include <cuda_runtime.h>
#include <cuda_bf16.h>
#include <cuda.h>
#include <stdint.h>

namespace tbl {
constexpr double PI = 3.14159265358979323846264338327950288;
constexpr double sin_s(double x) { double t = x, s = x; for (int n = 1; n < 12; n++) { t *= -x * x / ((2 * n) * (2 * n + 1)); s += t; } return s; }
constexpr double cos_s(double x) { double t = 1, s = 1; for (int n = 1; n < 12; n++) { t *= -x * x / ((2 * n - 1) * (2 * n)); s += t; } return s; }
constexpr double cos2048(int m) {
  m &= 2047; if (m > 1024) m = 2048 - m;
  bool neg = false; if (m > 512) { m = 1024 - m; neg = true; }
  double v = (m <= 256) ? cos_s(2 * PI * m / 2048) : sin_s(2 * PI * (512 - m) / 2048);
  return neg ? -v : v;
}
constexpr uint16_t to_bf16(double v) {
  if (v == 0) return 0;
  uint16_t s = 0; if (v < 0) { s = 0x8000; v = -v; }
  int e = 0; while (v >= 2) { v /= 2; e++; } while (v < 1) { v *= 2; e--; }
  double m = (v - 1) * 128; int mi = (int)m; double fr = m - mi;
  if (fr > 0.5 || (fr == 0.5 && (mi & 1))) mi++;
  if (mi == 128) { mi = 0; e++; }
  return (uint16_t)(s | ((e + 127) << 7) | mi);
}
struct CosT { uint16_t v[2048]; constexpr CosT() : v() { for (int i = 0; i < 2048; i++) v[i] = to_bf16(cos2048(i)); } };
struct alignas(1024) FT {
  uint16_t v[512 * 512];
  constexpr FT() : v() {
    CosT c;
    for (int r = 0; r < 512; r++) {
      int k = (r >> 4) * 8 + (r & 7), e = (r >> 3) & 1;
      int mul = 4 * k, add = e ? 512 : 0;
      if (k == 0 && e == 1) { mul = 1024; add = 0; }
      for (int d = 0; d < 512; d++) v[r * 512 + d] = c.v[(d * mul + add) & 2047];
    }
  }
};
struct alignas(1024) ET {
  uint16_t v[2048 * 128];
  constexpr ET() : v() {
    CosT c;
    for (int s = 0; s < 2048; s++)
      for (int j = 0; j < 64; j++) {
        const int o = (s & 31) * 8192 + (s >> 5) * 64 + j;
        v[o] = c.v[(s * j) & 2047]; v[o + 4096] = c.v[(s * j + 512) & 2047];
      }
  }
};
struct alignas(1024) DT {
  uint16_t v[64 * 64];
  constexpr DT() : v() {
    CosT c;
    for (int r = 0; r < 64; r++)
      for (int n = 0; n < 64; n++) {
        const int sg = r >> 1, s0 = (sg & ~6) | ((sg & 2) << 1) | ((sg & 4) >> 1), e = r & 1, f = n & 1;
        const int m = 64 * s0 * (n >> 1) + (e == f ? 0 : e ? -512 : 512);
        v[r * 64 + (((n >> 3) ^ (r & 7)) << 3) + (n & 7)] = c.v[m & 2047];
      }
  }
};
}

__device__ constexpr tbl::FT g_FT = tbl::FT();
__device__ constexpr tbl::ET g_ET = tbl::ET();
__device__ constexpr tbl::DT g_DT = tbl::DT();

struct alignas(1024) Work {
  unsigned epoch[132 * 8];
  unsigned cntX[8 * 32], cntT[8 * 32], cntP[128 * 32], cntW[32], cntH[32];
  alignas(16) float gate[16 * 128];
  alignas(16) uint2 Wh[2 * 2048];
  alignas(16) uint2 Ts[32 * 64];
  alignas(1024) uint16_t X[129 * 8192];
  alignas(1024) uint16_t T[32 * 64 * 512];
  alignas(1024) uint4 part[128 * 3 * 1024];
};
__device__ Work g_work;
#define PROF_EV(i) do {} while (0)
#define PROF_CK(i) do {} while (0)

__device__ __forceinline__ uint32_t smem_u32(const void* p) { return (uint32_t)__cvta_generic_to_shared(p); }
__device__ __forceinline__ void mbar_init(uint32_t bar, uint32_t cnt) { asm volatile("mbarrier.init.shared::cta.b64 [%0], %1;" ::"r"(bar), "r"(cnt)); }
__device__ __forceinline__ void mbar_expect_tx(uint32_t bar, uint32_t bytes) { asm volatile("mbarrier.arrive.expect_tx.shared::cta.b64 _, [%0], %1;" ::"r"(bar), "r"(bytes) : "memory"); }
__device__ __forceinline__ void mbar_arrive(uint32_t bar) { asm volatile("mbarrier.arrive.shared::cta.b64 _, [%0];" ::"r"(bar) : "memory"); }
__device__ __forceinline__ bool elect_one() {
  uint32_t p;
  asm volatile("{\n.reg .pred p;\nelect.sync _|p, 0xffffffff;\nselp.u32 %0, 1, 0, p;\n}" : "=r"(p));
  return p;
}
__device__ __forceinline__ void mbar_arrive_if(bool p, uint32_t bar) {
  asm volatile("{\n.reg .pred p;\nsetp.ne.b32 p, %1, 0;\n@p mbarrier.arrive.shared::cta.b64 _, [%0];\n}" ::"r"(bar), "r"((int)p) : "memory");
}
__device__ __forceinline__ void hint_add_if(bool p, unsigned* a) {
  asm volatile("{\n.reg .pred p;\nsetp.ne.b32 p, %1, 0;\n@p red.relaxed.gpu.global.add.u32 [%0], 1;\n}" ::"l"(a), "r"((int)p) : "memory");
}
__device__ __forceinline__ bool mbar_try(uint32_t bar, uint32_t parity) {
  uint32_t ok;
  asm volatile("{\n.reg .pred p;\nmbarrier.test_wait.parity.shared::cta.b64 p, [%1], %2;\nselp.u32 %0, 1, 0, p;\n}" : "=r"(ok) : "r"(bar), "r"(parity) : "memory");
  return ok;
}
__device__ __forceinline__ void mbar_wait(uint32_t bar, uint32_t parity) {
  asm volatile(
      "{\n.reg .pred p;\n.reg .u32 n;\nmov.u32 n, 0;\n"
      "W_LOOP:\nmbarrier.try_wait.parity.shared::cta.b64 p, [%0], %1;\n@p bra W_DONE;\n"
      "add.u32 n, n, 1;\nsetp.lt.u32 p, n, 0x40000;\n@p bra W_LOOP;\ntrap;\nW_DONE:\n}" ::"r"(bar), "r"(parity) : "memory");
}
__device__ __forceinline__ void bulk_load(uint32_t dst, const void* src, uint32_t bytes, uint32_t bar) {
  asm volatile("cp.async.bulk.shared::cluster.global.mbarrier::complete_tx::bytes [%0], [%1], %2, [%3];" ::"r"(dst), "l"(src), "r"(bytes), "r"(bar) : "memory");
}
__device__ __forceinline__ void cp16(uint32_t dst, const void* src) { asm volatile("cp.async.cg.shared.global [%0], [%1], 16;" ::"r"(dst), "l"(src) : "memory"); }
__device__ __forceinline__ void spin_guard(uint32_t t0) { if ((uint32_t)clock() - t0 > (1u << 30)) __trap(); }
__device__ __forceinline__ float tagf(float v, uint32_t tag) { return __uint_as_float((__float_as_uint(v) & ~1u) | tag); }
__device__ __forceinline__ float untag(float v) { return __uint_as_float(__float_as_uint(v) & ~1u); }
__device__ __forceinline__ void st_x2(float2* p, float a, float b) { asm volatile("st.relaxed.gpu.global.v2.f32 [%0], {%1,%2};" ::"l"(p), "f"(a), "f"(b) : "memory"); }
__device__ __forceinline__ float2 ld_x2(const float2* p) { float2 v; asm volatile("ld.relaxed.gpu.global.v2.f32 {%0,%1}, [%2];" : "=f"(v.x), "=f"(v.y) : "l"(p) : "memory"); return v; }
__device__ __forceinline__ void st_u2(uint2* p, uint32_t a, uint32_t b) { asm volatile("st.relaxed.gpu.global.v2.u32 [%0], {%1,%2};" ::"l"(p), "r"(a), "r"(b) : "memory"); }
__device__ __forceinline__ void prefetch2d(const CUtensorMap* m, int c0, int c1) { asm volatile("cp.async.bulk.prefetch.tensor.2d.L2.global [%0, {%1, %2}];" ::"l"(m), "r"(c0), "r"(c1) : "memory"); }
__device__ __forceinline__ void prefetch1d(const void* p, uint32_t bytes) { asm volatile("cp.async.bulk.prefetch.L2.global [%0], %1;" ::"l"(p), "r"(bytes) : "memory"); }
__device__ __forceinline__ uint32_t ld_x1(const void* p) { uint32_t v; asm volatile("ld.relaxed.gpu.global.u32 %0, [%1];" : "=r"(v) : "l"(p) : "memory"); return v; }
__device__ __forceinline__ uint4 ld_x4(const void* p) { uint4 v; asm volatile("ld.relaxed.gpu.global.v4.u32 {%0,%1,%2,%3}, [%4];" : "=r"(v.x), "=r"(v.y), "=r"(v.z), "=r"(v.w) : "l"(p) : "memory"); return v; }
__device__ __forceinline__ void st_x4(void* p, uint32_t a, uint32_t b, uint32_t c, uint32_t d) { asm volatile("st.relaxed.gpu.global.v4.u32 [%0], {%1,%2,%3,%4};" ::"l"(p), "r"(a), "r"(b), "r"(c), "r"(d) : "memory"); }
__device__ __forceinline__ uint32_t mapa(uint32_t a, uint32_t cta) { uint32_t r; asm volatile("mapa.shared::cluster.u32 %0, %1, %2;" : "=r"(r) : "r"(a), "r"(cta)); return r; }
__device__ __forceinline__ void stsm4t(uint32_t a, uint32_t r0, uint32_t r1, uint32_t r2, uint32_t r3) {
  asm volatile("stmatrix.sync.aligned.m8n8.x4.trans.shared.b16 [%0], {%1,%2,%3,%4};" ::"r"(a), "r"(r0), "r"(r1), "r"(r2), "r"(r3) : "memory");
}
__device__ __forceinline__ void hint_add(unsigned* p) { asm volatile("red.relaxed.gpu.global.add.u32 [%0], 1;" ::"l"(p) : "memory"); }
__device__ __forceinline__ void hint_wait(const unsigned* p, unsigned target) {
  const uint32_t t0 = (uint32_t)clock();
  while ((int)(ld_x1(p) - target) < 0) spin_guard(t0);
}
__device__ __forceinline__ void bulk_done_signal(unsigned* p) {
  asm volatile("cp.async.bulk.commit_group;\ncp.async.bulk.wait_group 0;\nfence.proxy.async.global;" ::: "memory");
  hint_add(p);
}
__device__ __forceinline__ void flag_wait(const unsigned* p, unsigned target) {
  hint_wait(p, target);
  asm volatile("fence.proxy.async.global;" ::: "memory");
}
__device__ __forceinline__ void tma2d(uint32_t dst, const CUtensorMap* m, uint32_t bar, int c0, int c1) {
  asm volatile("cp.async.bulk.tensor.2d.shared::cluster.global.mbarrier::complete_tx::bytes [%0], [%1, {%3, %4}], [%2];" ::"r"(dst), "l"(m), "r"(bar), "r"(c0), "r"(c1) : "memory");
}
__device__ __forceinline__ void tma3d(uint32_t dst, const CUtensorMap* m, uint32_t bar, int c0, int c1, int c2) {
  asm volatile("cp.async.bulk.tensor.3d.shared::cluster.global.mbarrier::complete_tx::bytes [%0], [%1, {%3, %4, %5}], [%2];" ::"r"(dst), "l"(m), "r"(bar), "r"(c0), "r"(c1), "r"(c2) : "memory");
}
__device__ __forceinline__ void tma4d(uint32_t dst, const CUtensorMap* m, uint32_t bar, int c0, int c1, int c2, int c3) {
  asm volatile("cp.async.bulk.tensor.4d.shared::cluster.global.mbarrier::complete_tx::bytes [%0], [%1, {%3, %4, %5, %6}], [%2];" ::"r"(dst), "l"(m), "r"(bar), "r"(c0), "r"(c1), "r"(c2), "r"(c3) : "memory");
}
__device__ __forceinline__ void wg_fence() { asm volatile("wgmma.fence.sync.aligned;" ::: "memory"); }
__device__ __forceinline__ void wg_commit() { asm volatile("wgmma.commit_group.sync.aligned;" ::: "memory"); }
template <int N> __device__ __forceinline__ void wg_wait() { asm volatile("wgmma.wait_group.sync.aligned %0;" ::"n"(N) : "memory"); }
template <int O, int N, int NN> __device__ __forceinline__ void fence_regs(float (&d)[NN]) {
#pragma unroll
  for (int i = 0; i < N; i++) asm volatile("" : "+f"(d[O + i])::"memory");
}
__device__ __forceinline__ uint32_t pack_bf16(float lo, float hi) {
  uint32_t r; asm("cvt.rn.bf16x2.f32 %0, %1, %2;" : "=r"(r) : "f"(hi), "f"(lo)); return r;
}
__device__ __forceinline__ uint32_t pack_pin(float lo, float hi) {
  uint32_t r; asm volatile("cvt.rn.bf16x2.f32 %0, %1, %2;" : "=r"(r) : "f"(hi), "f"(lo) : "memory"); return r;
}
__device__ __forceinline__ float bf_lo(uint32_t u) { return __uint_as_float(u << 16); }
__device__ __forceinline__ float bf_hi(uint32_t u) { return __uint_as_float(u & 0xffff0000u); }

__device__ __forceinline__ uint64_t d128(uint32_t lo) { uint64_t d; asm("mov.b64 %0, {%1, 0x40000040};" : "=l"(d) : "r"(lo)); return d; }
__device__ __forceinline__ uint64_t d64(uint32_t lo) { uint64_t d; asm("mov.b64 %0, {%1, 0x80000020};" : "=l"(d) : "r"(lo)); return d; }
template<int O,int TB,int ACC,int NN> __device__ __forceinline__ void mma_ss64(float (&d)[NN], uint64_t da, uint64_t db, int sd = 0){
  if constexpr (ACC == 1) asm volatile("wgmma.mma_async.sync.aligned.m64n64k16.f32.bf16.bf16 {%0,%1,%2,%3,%4,%5,%6,%7,%8,%9,%10,%11,%12,%13,%14,%15,%16,%17,%18,%19,%20,%21,%22,%23,%24,%25,%26,%27,%28,%29,%30,%31}, %32, %33, 1, 1, 1, %35, %34;"
   : "+f"(d[O+0]), "+f"(d[O+1]), "+f"(d[O+2]), "+f"(d[O+3]), "+f"(d[O+4]), "+f"(d[O+5]), "+f"(d[O+6]), "+f"(d[O+7]), "+f"(d[O+8]), "+f"(d[O+9]), "+f"(d[O+10]), "+f"(d[O+11]), "+f"(d[O+12]), "+f"(d[O+13]), "+f"(d[O+14]), "+f"(d[O+15]), "+f"(d[O+16]), "+f"(d[O+17]), "+f"(d[O+18]), "+f"(d[O+19]), "+f"(d[O+20]), "+f"(d[O+21]), "+f"(d[O+22]), "+f"(d[O+23]), "+f"(d[O+24]), "+f"(d[O+25]), "+f"(d[O+26]), "+f"(d[O+27]), "+f"(d[O+28]), "+f"(d[O+29]), "+f"(d[O+30]), "+f"(d[O+31])
   : "l"(da), "l"(db), "n"(TB & 1), "n"(TB >> 1));
  else if constexpr (ACC == 0) asm volatile("wgmma.mma_async.sync.aligned.m64n64k16.f32.bf16.bf16 {%0,%1,%2,%3,%4,%5,%6,%7,%8,%9,%10,%11,%12,%13,%14,%15,%16,%17,%18,%19,%20,%21,%22,%23,%24,%25,%26,%27,%28,%29,%30,%31}, %32, %33, 0, 1, 1, %35, %34;"
   : "=f"(d[O+0]), "=f"(d[O+1]), "=f"(d[O+2]), "=f"(d[O+3]), "=f"(d[O+4]), "=f"(d[O+5]), "=f"(d[O+6]), "=f"(d[O+7]), "=f"(d[O+8]), "=f"(d[O+9]), "=f"(d[O+10]), "=f"(d[O+11]), "=f"(d[O+12]), "=f"(d[O+13]), "=f"(d[O+14]), "=f"(d[O+15]), "=f"(d[O+16]), "=f"(d[O+17]), "=f"(d[O+18]), "=f"(d[O+19]), "=f"(d[O+20]), "=f"(d[O+21]), "=f"(d[O+22]), "=f"(d[O+23]), "=f"(d[O+24]), "=f"(d[O+25]), "=f"(d[O+26]), "=f"(d[O+27]), "=f"(d[O+28]), "=f"(d[O+29]), "=f"(d[O+30]), "=f"(d[O+31])
   : "l"(da), "l"(db), "n"(TB & 1), "n"(TB >> 1));
  else asm volatile("{\n.reg .pred p;\nsetp.ne.b32 p, %36, 0;\nwgmma.mma_async.sync.aligned.m64n64k16.f32.bf16.bf16 {%0,%1,%2,%3,%4,%5,%6,%7,%8,%9,%10,%11,%12,%13,%14,%15,%16,%17,%18,%19,%20,%21,%22,%23,%24,%25,%26,%27,%28,%29,%30,%31}, %32, %33, p, 1, 1, %35, %34;\n}"
   : "+f"(d[O+0]), "+f"(d[O+1]), "+f"(d[O+2]), "+f"(d[O+3]), "+f"(d[O+4]), "+f"(d[O+5]), "+f"(d[O+6]), "+f"(d[O+7]), "+f"(d[O+8]), "+f"(d[O+9]), "+f"(d[O+10]), "+f"(d[O+11]), "+f"(d[O+12]), "+f"(d[O+13]), "+f"(d[O+14]), "+f"(d[O+15]), "+f"(d[O+16]), "+f"(d[O+17]), "+f"(d[O+18]), "+f"(d[O+19]), "+f"(d[O+20]), "+f"(d[O+21]), "+f"(d[O+22]), "+f"(d[O+23]), "+f"(d[O+24]), "+f"(d[O+25]), "+f"(d[O+26]), "+f"(d[O+27]), "+f"(d[O+28]), "+f"(d[O+29]), "+f"(d[O+30]), "+f"(d[O+31])
   : "l"(da), "l"(db), "n"(TB & 1), "n"(TB >> 1), "r"(sd));
}
template<int O,int TB,int ACC,int NN> __device__ __forceinline__ void mma_rs64(float (&d)[NN], uint32_t a0, uint32_t a1, uint32_t a2, uint32_t a3, uint64_t db, int sd = 0){
  if constexpr (ACC == 1) asm volatile("wgmma.mma_async.sync.aligned.m64n64k16.f32.bf16.bf16 {%0,%1,%2,%3,%4,%5,%6,%7,%8,%9,%10,%11,%12,%13,%14,%15,%16,%17,%18,%19,%20,%21,%22,%23,%24,%25,%26,%27,%28,%29,%30,%31}, {%32,%33,%34,%35}, %36, 1, 1, 1, %37;"
   : "+f"(d[O+0]), "+f"(d[O+1]), "+f"(d[O+2]), "+f"(d[O+3]), "+f"(d[O+4]), "+f"(d[O+5]), "+f"(d[O+6]), "+f"(d[O+7]), "+f"(d[O+8]), "+f"(d[O+9]), "+f"(d[O+10]), "+f"(d[O+11]), "+f"(d[O+12]), "+f"(d[O+13]), "+f"(d[O+14]), "+f"(d[O+15]), "+f"(d[O+16]), "+f"(d[O+17]), "+f"(d[O+18]), "+f"(d[O+19]), "+f"(d[O+20]), "+f"(d[O+21]), "+f"(d[O+22]), "+f"(d[O+23]), "+f"(d[O+24]), "+f"(d[O+25]), "+f"(d[O+26]), "+f"(d[O+27]), "+f"(d[O+28]), "+f"(d[O+29]), "+f"(d[O+30]), "+f"(d[O+31])
   : "r"(a0), "r"(a1), "r"(a2), "r"(a3), "l"(db), "n"(TB));
  else if constexpr (ACC == 0) asm volatile("wgmma.mma_async.sync.aligned.m64n64k16.f32.bf16.bf16 {%0,%1,%2,%3,%4,%5,%6,%7,%8,%9,%10,%11,%12,%13,%14,%15,%16,%17,%18,%19,%20,%21,%22,%23,%24,%25,%26,%27,%28,%29,%30,%31}, {%32,%33,%34,%35}, %36, 0, 1, 1, %37;"
   : "=f"(d[O+0]), "=f"(d[O+1]), "=f"(d[O+2]), "=f"(d[O+3]), "=f"(d[O+4]), "=f"(d[O+5]), "=f"(d[O+6]), "=f"(d[O+7]), "=f"(d[O+8]), "=f"(d[O+9]), "=f"(d[O+10]), "=f"(d[O+11]), "=f"(d[O+12]), "=f"(d[O+13]), "=f"(d[O+14]), "=f"(d[O+15]), "=f"(d[O+16]), "=f"(d[O+17]), "=f"(d[O+18]), "=f"(d[O+19]), "=f"(d[O+20]), "=f"(d[O+21]), "=f"(d[O+22]), "=f"(d[O+23]), "=f"(d[O+24]), "=f"(d[O+25]), "=f"(d[O+26]), "=f"(d[O+27]), "=f"(d[O+28]), "=f"(d[O+29]), "=f"(d[O+30]), "=f"(d[O+31])
   : "r"(a0), "r"(a1), "r"(a2), "r"(a3), "l"(db), "n"(TB));
  else asm volatile("{\n.reg .pred p;\nsetp.ne.b32 p, %38, 0;\nwgmma.mma_async.sync.aligned.m64n64k16.f32.bf16.bf16 {%0,%1,%2,%3,%4,%5,%6,%7,%8,%9,%10,%11,%12,%13,%14,%15,%16,%17,%18,%19,%20,%21,%22,%23,%24,%25,%26,%27,%28,%29,%30,%31}, {%32,%33,%34,%35}, %36, p, 1, 1, %37;\n}"
   : "+f"(d[O+0]), "+f"(d[O+1]), "+f"(d[O+2]), "+f"(d[O+3]), "+f"(d[O+4]), "+f"(d[O+5]), "+f"(d[O+6]), "+f"(d[O+7]), "+f"(d[O+8]), "+f"(d[O+9]), "+f"(d[O+10]), "+f"(d[O+11]), "+f"(d[O+12]), "+f"(d[O+13]), "+f"(d[O+14]), "+f"(d[O+15]), "+f"(d[O+16]), "+f"(d[O+17]), "+f"(d[O+18]), "+f"(d[O+19]), "+f"(d[O+20]), "+f"(d[O+21]), "+f"(d[O+22]), "+f"(d[O+23]), "+f"(d[O+24]), "+f"(d[O+25]), "+f"(d[O+26]), "+f"(d[O+27]), "+f"(d[O+28]), "+f"(d[O+29]), "+f"(d[O+30]), "+f"(d[O+31])
   : "r"(a0), "r"(a1), "r"(a2), "r"(a3), "l"(db), "n"(TB), "r"(sd));
}
template<int O,int TB,int ACC,int NN> __device__ __forceinline__ void mma_ss128(float (&d)[NN], uint64_t da, uint64_t db, int sd = 0){
  if constexpr (ACC == 1) asm volatile("wgmma.mma_async.sync.aligned.m64n128k16.f32.bf16.bf16 {%0,%1,%2,%3,%4,%5,%6,%7,%8,%9,%10,%11,%12,%13,%14,%15,%16,%17,%18,%19,%20,%21,%22,%23,%24,%25,%26,%27,%28,%29,%30,%31,%32,%33,%34,%35,%36,%37,%38,%39,%40,%41,%42,%43,%44,%45,%46,%47,%48,%49,%50,%51,%52,%53,%54,%55,%56,%57,%58,%59,%60,%61,%62,%63}, %64, %65, 1, 1, 1, %67, %66;"
   : "+f"(d[O+0]), "+f"(d[O+1]), "+f"(d[O+2]), "+f"(d[O+3]), "+f"(d[O+4]), "+f"(d[O+5]), "+f"(d[O+6]), "+f"(d[O+7]), "+f"(d[O+8]), "+f"(d[O+9]), "+f"(d[O+10]), "+f"(d[O+11]), "+f"(d[O+12]), "+f"(d[O+13]), "+f"(d[O+14]), "+f"(d[O+15]), "+f"(d[O+16]), "+f"(d[O+17]), "+f"(d[O+18]), "+f"(d[O+19]), "+f"(d[O+20]), "+f"(d[O+21]), "+f"(d[O+22]), "+f"(d[O+23]), "+f"(d[O+24]), "+f"(d[O+25]), "+f"(d[O+26]), "+f"(d[O+27]), "+f"(d[O+28]), "+f"(d[O+29]), "+f"(d[O+30]), "+f"(d[O+31]), "+f"(d[O+32]), "+f"(d[O+33]), "+f"(d[O+34]), "+f"(d[O+35]), "+f"(d[O+36]), "+f"(d[O+37]), "+f"(d[O+38]), "+f"(d[O+39]), "+f"(d[O+40]), "+f"(d[O+41]), "+f"(d[O+42]), "+f"(d[O+43]), "+f"(d[O+44]), "+f"(d[O+45]), "+f"(d[O+46]), "+f"(d[O+47]), "+f"(d[O+48]), "+f"(d[O+49]), "+f"(d[O+50]), "+f"(d[O+51]), "+f"(d[O+52]), "+f"(d[O+53]), "+f"(d[O+54]), "+f"(d[O+55]), "+f"(d[O+56]), "+f"(d[O+57]), "+f"(d[O+58]), "+f"(d[O+59]), "+f"(d[O+60]), "+f"(d[O+61]), "+f"(d[O+62]), "+f"(d[O+63])
   : "l"(da), "l"(db), "n"(TB & 1), "n"(TB >> 1));
  else if constexpr (ACC == 0) asm volatile("wgmma.mma_async.sync.aligned.m64n128k16.f32.bf16.bf16 {%0,%1,%2,%3,%4,%5,%6,%7,%8,%9,%10,%11,%12,%13,%14,%15,%16,%17,%18,%19,%20,%21,%22,%23,%24,%25,%26,%27,%28,%29,%30,%31,%32,%33,%34,%35,%36,%37,%38,%39,%40,%41,%42,%43,%44,%45,%46,%47,%48,%49,%50,%51,%52,%53,%54,%55,%56,%57,%58,%59,%60,%61,%62,%63}, %64, %65, 0, 1, 1, %67, %66;"
   : "=f"(d[O+0]), "=f"(d[O+1]), "=f"(d[O+2]), "=f"(d[O+3]), "=f"(d[O+4]), "=f"(d[O+5]), "=f"(d[O+6]), "=f"(d[O+7]), "=f"(d[O+8]), "=f"(d[O+9]), "=f"(d[O+10]), "=f"(d[O+11]), "=f"(d[O+12]), "=f"(d[O+13]), "=f"(d[O+14]), "=f"(d[O+15]), "=f"(d[O+16]), "=f"(d[O+17]), "=f"(d[O+18]), "=f"(d[O+19]), "=f"(d[O+20]), "=f"(d[O+21]), "=f"(d[O+22]), "=f"(d[O+23]), "=f"(d[O+24]), "=f"(d[O+25]), "=f"(d[O+26]), "=f"(d[O+27]), "=f"(d[O+28]), "=f"(d[O+29]), "=f"(d[O+30]), "=f"(d[O+31]), "=f"(d[O+32]), "=f"(d[O+33]), "=f"(d[O+34]), "=f"(d[O+35]), "=f"(d[O+36]), "=f"(d[O+37]), "=f"(d[O+38]), "=f"(d[O+39]), "=f"(d[O+40]), "=f"(d[O+41]), "=f"(d[O+42]), "=f"(d[O+43]), "=f"(d[O+44]), "=f"(d[O+45]), "=f"(d[O+46]), "=f"(d[O+47]), "=f"(d[O+48]), "=f"(d[O+49]), "=f"(d[O+50]), "=f"(d[O+51]), "=f"(d[O+52]), "=f"(d[O+53]), "=f"(d[O+54]), "=f"(d[O+55]), "=f"(d[O+56]), "=f"(d[O+57]), "=f"(d[O+58]), "=f"(d[O+59]), "=f"(d[O+60]), "=f"(d[O+61]), "=f"(d[O+62]), "=f"(d[O+63])
   : "l"(da), "l"(db), "n"(TB & 1), "n"(TB >> 1));
  else asm volatile("{\n.reg .pred p;\nsetp.ne.b32 p, %68, 0;\nwgmma.mma_async.sync.aligned.m64n128k16.f32.bf16.bf16 {%0,%1,%2,%3,%4,%5,%6,%7,%8,%9,%10,%11,%12,%13,%14,%15,%16,%17,%18,%19,%20,%21,%22,%23,%24,%25,%26,%27,%28,%29,%30,%31,%32,%33,%34,%35,%36,%37,%38,%39,%40,%41,%42,%43,%44,%45,%46,%47,%48,%49,%50,%51,%52,%53,%54,%55,%56,%57,%58,%59,%60,%61,%62,%63}, %64, %65, p, 1, 1, %67, %66;\n}"
   : "+f"(d[O+0]), "+f"(d[O+1]), "+f"(d[O+2]), "+f"(d[O+3]), "+f"(d[O+4]), "+f"(d[O+5]), "+f"(d[O+6]), "+f"(d[O+7]), "+f"(d[O+8]), "+f"(d[O+9]), "+f"(d[O+10]), "+f"(d[O+11]), "+f"(d[O+12]), "+f"(d[O+13]), "+f"(d[O+14]), "+f"(d[O+15]), "+f"(d[O+16]), "+f"(d[O+17]), "+f"(d[O+18]), "+f"(d[O+19]), "+f"(d[O+20]), "+f"(d[O+21]), "+f"(d[O+22]), "+f"(d[O+23]), "+f"(d[O+24]), "+f"(d[O+25]), "+f"(d[O+26]), "+f"(d[O+27]), "+f"(d[O+28]), "+f"(d[O+29]), "+f"(d[O+30]), "+f"(d[O+31]), "+f"(d[O+32]), "+f"(d[O+33]), "+f"(d[O+34]), "+f"(d[O+35]), "+f"(d[O+36]), "+f"(d[O+37]), "+f"(d[O+38]), "+f"(d[O+39]), "+f"(d[O+40]), "+f"(d[O+41]), "+f"(d[O+42]), "+f"(d[O+43]), "+f"(d[O+44]), "+f"(d[O+45]), "+f"(d[O+46]), "+f"(d[O+47]), "+f"(d[O+48]), "+f"(d[O+49]), "+f"(d[O+50]), "+f"(d[O+51]), "+f"(d[O+52]), "+f"(d[O+53]), "+f"(d[O+54]), "+f"(d[O+55]), "+f"(d[O+56]), "+f"(d[O+57]), "+f"(d[O+58]), "+f"(d[O+59]), "+f"(d[O+60]), "+f"(d[O+61]), "+f"(d[O+62]), "+f"(d[O+63])
   : "l"(da), "l"(db), "n"(TB & 1), "n"(TB >> 1), "r"(sd));
}
template<int O,int TB,int ACC,int NN> __device__ __forceinline__ void mma_rs128(float (&d)[NN], uint32_t a0, uint32_t a1, uint32_t a2, uint32_t a3, uint64_t db, int sd = 0){
  if constexpr (ACC == 1) asm volatile("wgmma.mma_async.sync.aligned.m64n128k16.f32.bf16.bf16 {%0,%1,%2,%3,%4,%5,%6,%7,%8,%9,%10,%11,%12,%13,%14,%15,%16,%17,%18,%19,%20,%21,%22,%23,%24,%25,%26,%27,%28,%29,%30,%31,%32,%33,%34,%35,%36,%37,%38,%39,%40,%41,%42,%43,%44,%45,%46,%47,%48,%49,%50,%51,%52,%53,%54,%55,%56,%57,%58,%59,%60,%61,%62,%63}, {%64,%65,%66,%67}, %68, 1, 1, 1, %69;"
   : "+f"(d[O+0]), "+f"(d[O+1]), "+f"(d[O+2]), "+f"(d[O+3]), "+f"(d[O+4]), "+f"(d[O+5]), "+f"(d[O+6]), "+f"(d[O+7]), "+f"(d[O+8]), "+f"(d[O+9]), "+f"(d[O+10]), "+f"(d[O+11]), "+f"(d[O+12]), "+f"(d[O+13]), "+f"(d[O+14]), "+f"(d[O+15]), "+f"(d[O+16]), "+f"(d[O+17]), "+f"(d[O+18]), "+f"(d[O+19]), "+f"(d[O+20]), "+f"(d[O+21]), "+f"(d[O+22]), "+f"(d[O+23]), "+f"(d[O+24]), "+f"(d[O+25]), "+f"(d[O+26]), "+f"(d[O+27]), "+f"(d[O+28]), "+f"(d[O+29]), "+f"(d[O+30]), "+f"(d[O+31]), "+f"(d[O+32]), "+f"(d[O+33]), "+f"(d[O+34]), "+f"(d[O+35]), "+f"(d[O+36]), "+f"(d[O+37]), "+f"(d[O+38]), "+f"(d[O+39]), "+f"(d[O+40]), "+f"(d[O+41]), "+f"(d[O+42]), "+f"(d[O+43]), "+f"(d[O+44]), "+f"(d[O+45]), "+f"(d[O+46]), "+f"(d[O+47]), "+f"(d[O+48]), "+f"(d[O+49]), "+f"(d[O+50]), "+f"(d[O+51]), "+f"(d[O+52]), "+f"(d[O+53]), "+f"(d[O+54]), "+f"(d[O+55]), "+f"(d[O+56]), "+f"(d[O+57]), "+f"(d[O+58]), "+f"(d[O+59]), "+f"(d[O+60]), "+f"(d[O+61]), "+f"(d[O+62]), "+f"(d[O+63])
   : "r"(a0), "r"(a1), "r"(a2), "r"(a3), "l"(db), "n"(TB));
  else if constexpr (ACC == 0) asm volatile("wgmma.mma_async.sync.aligned.m64n128k16.f32.bf16.bf16 {%0,%1,%2,%3,%4,%5,%6,%7,%8,%9,%10,%11,%12,%13,%14,%15,%16,%17,%18,%19,%20,%21,%22,%23,%24,%25,%26,%27,%28,%29,%30,%31,%32,%33,%34,%35,%36,%37,%38,%39,%40,%41,%42,%43,%44,%45,%46,%47,%48,%49,%50,%51,%52,%53,%54,%55,%56,%57,%58,%59,%60,%61,%62,%63}, {%64,%65,%66,%67}, %68, 0, 1, 1, %69;"
   : "=f"(d[O+0]), "=f"(d[O+1]), "=f"(d[O+2]), "=f"(d[O+3]), "=f"(d[O+4]), "=f"(d[O+5]), "=f"(d[O+6]), "=f"(d[O+7]), "=f"(d[O+8]), "=f"(d[O+9]), "=f"(d[O+10]), "=f"(d[O+11]), "=f"(d[O+12]), "=f"(d[O+13]), "=f"(d[O+14]), "=f"(d[O+15]), "=f"(d[O+16]), "=f"(d[O+17]), "=f"(d[O+18]), "=f"(d[O+19]), "=f"(d[O+20]), "=f"(d[O+21]), "=f"(d[O+22]), "=f"(d[O+23]), "=f"(d[O+24]), "=f"(d[O+25]), "=f"(d[O+26]), "=f"(d[O+27]), "=f"(d[O+28]), "=f"(d[O+29]), "=f"(d[O+30]), "=f"(d[O+31]), "=f"(d[O+32]), "=f"(d[O+33]), "=f"(d[O+34]), "=f"(d[O+35]), "=f"(d[O+36]), "=f"(d[O+37]), "=f"(d[O+38]), "=f"(d[O+39]), "=f"(d[O+40]), "=f"(d[O+41]), "=f"(d[O+42]), "=f"(d[O+43]), "=f"(d[O+44]), "=f"(d[O+45]), "=f"(d[O+46]), "=f"(d[O+47]), "=f"(d[O+48]), "=f"(d[O+49]), "=f"(d[O+50]), "=f"(d[O+51]), "=f"(d[O+52]), "=f"(d[O+53]), "=f"(d[O+54]), "=f"(d[O+55]), "=f"(d[O+56]), "=f"(d[O+57]), "=f"(d[O+58]), "=f"(d[O+59]), "=f"(d[O+60]), "=f"(d[O+61]), "=f"(d[O+62]), "=f"(d[O+63])
   : "r"(a0), "r"(a1), "r"(a2), "r"(a3), "l"(db), "n"(TB));
  else asm volatile("{\n.reg .pred p;\nsetp.ne.b32 p, %70, 0;\nwgmma.mma_async.sync.aligned.m64n128k16.f32.bf16.bf16 {%0,%1,%2,%3,%4,%5,%6,%7,%8,%9,%10,%11,%12,%13,%14,%15,%16,%17,%18,%19,%20,%21,%22,%23,%24,%25,%26,%27,%28,%29,%30,%31,%32,%33,%34,%35,%36,%37,%38,%39,%40,%41,%42,%43,%44,%45,%46,%47,%48,%49,%50,%51,%52,%53,%54,%55,%56,%57,%58,%59,%60,%61,%62,%63}, {%64,%65,%66,%67}, %68, p, 1, 1, %69;\n}"
   : "+f"(d[O+0]), "+f"(d[O+1]), "+f"(d[O+2]), "+f"(d[O+3]), "+f"(d[O+4]), "+f"(d[O+5]), "+f"(d[O+6]), "+f"(d[O+7]), "+f"(d[O+8]), "+f"(d[O+9]), "+f"(d[O+10]), "+f"(d[O+11]), "+f"(d[O+12]), "+f"(d[O+13]), "+f"(d[O+14]), "+f"(d[O+15]), "+f"(d[O+16]), "+f"(d[O+17]), "+f"(d[O+18]), "+f"(d[O+19]), "+f"(d[O+20]), "+f"(d[O+21]), "+f"(d[O+22]), "+f"(d[O+23]), "+f"(d[O+24]), "+f"(d[O+25]), "+f"(d[O+26]), "+f"(d[O+27]), "+f"(d[O+28]), "+f"(d[O+29]), "+f"(d[O+30]), "+f"(d[O+31]), "+f"(d[O+32]), "+f"(d[O+33]), "+f"(d[O+34]), "+f"(d[O+35]), "+f"(d[O+36]), "+f"(d[O+37]), "+f"(d[O+38]), "+f"(d[O+39]), "+f"(d[O+40]), "+f"(d[O+41]), "+f"(d[O+42]), "+f"(d[O+43]), "+f"(d[O+44]), "+f"(d[O+45]), "+f"(d[O+46]), "+f"(d[O+47]), "+f"(d[O+48]), "+f"(d[O+49]), "+f"(d[O+50]), "+f"(d[O+51]), "+f"(d[O+52]), "+f"(d[O+53]), "+f"(d[O+54]), "+f"(d[O+55]), "+f"(d[O+56]), "+f"(d[O+57]), "+f"(d[O+58]), "+f"(d[O+59]), "+f"(d[O+60]), "+f"(d[O+61]), "+f"(d[O+62]), "+f"(d[O+63])
   : "r"(a0), "r"(a1), "r"(a2), "r"(a3), "l"(db), "n"(TB), "r"(sd));
}

#define NEARLY 0
#define XAHEAD 3
#define HEADN 6
#define WBATCH 1
#define WB 8
#define WSLEEP 20
#define XSPREAD 4
#define NOSEND 0
#define MSPLIT 3
#define PFALL 1
#define L2PF 1
#define STAG 0
#define EPF 2
#define XNB 2
#define FNB 0
#define GNB 0
#define TH 5
#define PF0 4
#define FSPLIT 1
#define MGLU 1
#define SPACE 40
#define WPF 1
#define WAFTER 7
#define WPACE 0
#define GATE_AT 4
#define TPACE 40
#define PFMODE 0
#define MAPMODE 1
template <int V> struct IC { static constexpr int value = V; };
struct Maps { CUtensorMap x, ft, g64, u64, e, wr, wi, xs, ts, t, g32, u32, d224, o; };

constexpr int NCTA = 130;
constexpr int U = 16384;
constexpr int TB = 36864;
constexpr int OFF_RING = 8 * U, OFF_Z = 9 * U, OFF_XB = 12 * U, OFF_T = 13 * U, OFF_D = OFF_T;
constexpr int OFF_BAR = 14 * U, OFF_SP = OFF_BAR + 512, OFF_G = OFF_SP + 1024 + 128;
constexpr int SMEM_BYTES = OFF_G + 512;
constexpr int B_FX = 0, B_FA = 8, B_FT = 12, B_Z = 16, B_W = 24, B_HX = 25, B_TL = 26, B_HP = 27, B_WR = 30, B_E0 = 34;
constexpr int B_EA = 35, B_ET = 39, B_PZ = 43, B_RDY = 45, B_FE = 46;
constexpr int B_T = 50, B_XS = 51, B_G = 53, NBAR = 54;
__host__ __device__ constexpr int rslot(int n) { return n & 3; }
__host__ __device__ constexpr int rpar(int n) { return (n >> 2) & 1; }

__global__ void __cluster_dims__(2, 1, 1) __launch_bounds__(512, 1)
fused_kernel(Work* __restrict__ ws, const uint16_t* __restrict__ dtab, const __nv_bfloat16* __restrict__ w_r, const __nv_bfloat16* __restrict__ w_i,
             const __nv_bfloat16* __restrict__ gate_w, const __nv_bfloat16* __restrict__ x, const uint16_t* __restrict__ ftab,
             const __nv_bfloat16* __restrict__ Wg, const __nv_bfloat16* __restrict__ Wu, const __grid_constant__ Maps maps) {
  extern __shared__ __align__(1024) uint8_t smem[];
  if (threadIdx.x < 32 && elect_one()) {
#pragma unroll
    for (int i = 0; i < PF0; i++) asm volatile("prefetch.tensormap [%0];" ::"l"((const char*)&maps + i * 128) : "memory");
  }
  const uint32_t sb = smem_u32(smem);
  const uint32_t bars = sb + OFF_BAR;
  const int tid = threadIdx.x, lane = tid & 31;
  const int warp = __shfl_sync(0xffffffffu, tid >> 5, 0);
  const bool helper = blockIdx.x >= 128;
  const int cl = (blockIdx.x >> 1) & 63, rank = blockIdx.x & 1;
  const int q4 = (cl & 1) | ((cl >> 2) & 2), rb = ((cl >> 1) & 3) | ((cl >> 4) << 2);
  const int j = 2 * q4 + rank;
  const int f_full = 448 * q4 + (rank ? 256 : 0);
  const int f_half = 448 * q4 + (rank ? 224 : 192);
  const int kg = 2 * j + (rb >> 3), tn = rb & 7;

  if (tid == 64) { PROF_EV(0); PROF_CK(40); }
  if (warp < 8) {
    if (!helper) {
      if (tid < 16 * XNB) {
        const int r = 16 * j + (tid & 15);
        asm volatile("prefetch.global.L2 [%0];" ::"l"(x + (size_t)(2 * rb + (r >> 6) + 32 * (r & 63)) * 512 + 64 * (tid >> 4)));
      } else if (tid >= 128 && tid < 128 + 4 * FNB) {
        asm volatile("prefetch.global.L2 [%0];" ::"l"(ftab + (64 * j + 4 * rb + (tid & 3)) * 512 + 64 * ((tid - 128) >> 2)));
      } else if (tid >= 192 && tid < 192 + 8 * GNB) {
        asm volatile("prefetch.global.L2 [%0];" ::"l"(((tid & 4) ? Wu : Wg) + (size_t)(64 * ((tid - 192) >> 3) + 4 * rb + (tid & 3)) * 1792 + f_full));
      }
    }
    asm volatile("barrier.cluster.arrive.relaxed.aligned;" ::: "memory");
    asm volatile("setmaxnreg.inc.sync.aligned.u32 192;");
    if (!helper) {
      const int wg = warp >> 2, w = warp & 3, g = lane >> 2;
      const bool elect = (tid & 127) == 0;
      float cX[32], cA[64], cB[64], cC[64], ci[64], ct[64];
      const int zero = blockIdx.x >> 16;
      uint32_t h[56], yf[16];
      const uint32_t d0 = (sb & 0x3FFFF) >> 4;
      const uint32_t dK = d0 | (1u << 16), dN = d0 | (512u << 16);
      const uint32_t dX = dK + wg * 512;
      constexpr uint32_t RING = OFF_RING >> 4;
      auto waitA = [&](int n) { mbar_wait(bars + 8 * (B_FA + rslot(n)), rpar(n)); };
      auto freeA = [&](int n) { mbar_arrive_if(elect, bars + 8 * (B_EA + rslot(n))); };
      auto nop = [] {};

      asm volatile("bar.sync 0, 384;" ::: "memory");
#pragma unroll 1
      for (int i = 0; i < 4; i++) {
        const uint64_t dx = d128(dX + i * 2048), df = d128(dK + (OFF_XB >> 4) + (i & 1) * 1024);
        mbar_wait(bars + 8 * (B_FX + 2 * i), 0);
        wg_fence();
        mma_ss64<0, 0, 2>(cX, df, dx, i);
        mma_ss64<0, 0, 1>(cX, df + 2, dx + 2);
        wg_commit(); wg_wait<1>();
        mbar_arrive_if(elect && i, bars + 8 * (B_EA + rslot(i - 1)));
        mma_ss64<0, 0, 1>(cX, df + 4, dx + 4);
        mma_ss64<0, 0, 1>(cX, df + 6, dx + 6);
        if (i == 0 && tid == 0) PROF_EV(1);
        mbar_wait(bars + 8 * (B_FX + 2 * i + 1), 0);
        wg_fence();
#pragma unroll
        for (int k = 0; k < 4; k++) mma_ss64<0, 0, 1>(cX, df + (512 + k * 2), dx + (1024 + k * 2));
        wg_commit();
        waitA(i);
        wg_fence();
        const uint64_t da = d128(dX + i * 1024), db = d128(dN + RING + i * 1024);
        mma_ss128<0, 1, 2>(cA, da, db, i);
        wg_commit(); wg_wait<1>();
        mbar_arrive_if(elect, bars + 8 * (B_FE + i));
#pragma unroll
        for (int k = 1; k < 4; k++) mma_ss128<0, 1, 1>(cA, da + k * 2, db + k * 128);
        wg_commit();
      }
      fence_regs<0, 32>(cX);
#pragma unroll
      for (int e = 0; e < 16; e++) yf[e] = pack_pin(cX[2 * e], cX[2 * e + 1]);
      if (tid == 0) { PROF_EV(2); PROF_CK(42); }
      {
        waitA(4); mbar_wait(bars + 8 * B_E0, 0);
        const uint64_t de = d128(dN + (wg ? RING : OFF_XB >> 4));
        wg_fence();
        mma_rs128<0, 1, 0>(cB, yf[0], yf[1], yf[2], yf[3], de);
        wg_commit();
        wg_wait<1>();
        freeA(3);
#pragma unroll
        for (int k = 1; k < 4; k++) mma_rs128<0, 1, 1>(cB, yf[4 * k], yf[4 * k + 1], yf[4 * k + 2], yf[4 * k + 3], de + k * 128);
        wg_commit();
      }
      bool rel = false;
      auto acquire = [&](int n) {
        rel = elect;
        if (!mbar_try(bars + 8 * (B_FA + rslot(n)), rpar(n))) { wg_wait<0>(); freeA(n - 1); rel = false; waitA(n); }
      };
      auto freeP = [&](int n) { mbar_arrive_if(rel, bars + 8 * (B_EA + rslot(n - 1))); };
      auto ffn_step = [&](auto first, auto split, float (&acc)[64], int n, int kb, auto done, auto work) {
        constexpr int SPLIT = decltype(split)::value;
        acquire(n);
        wg_fence();
        const uint64_t dx = d128(dX + kb * 1024), db = d128(dN + RING + rslot(n) * 1024);
        mma_ss128<0, 1, decltype(first)::value>(acc, dx, db, kb);
#pragma unroll
        for (int k = 1; k < SPLIT; k++) mma_ss128<0, 1, 1>(acc, dx + k * 2, db + k * 128);
        wg_commit();
        work();
        wg_wait<1>();
        freeP(n);
        done();
        if (SPLIT < 4) {
          wg_fence();
#pragma unroll
          for (int k = SPLIT; k < 4; k++) mma_ss128<0, 1, 1>(acc, dx + k * 2, db + k * 128);
          wg_commit();
        }
      };
      {
        const int s0 = 2 * rb + wg, kr = 2 * ((s0 & 1) | ((s0 & 4) >> 1));
        const int m = lane >> 3, r = lane & 7;
        const uint32_t a0 = sb + OFF_XB + wg * 8192 + (((w >> 1) * 8 + (m >> 1)) * 2 + (w & 1)) * 256 + (m & 1) * 128 + ((r ^ (kr + (m & 1))) << 4);
        ffn_step(IC<1>(), IC<4>(), cA, 5, 4, [&] { fence_regs<0, 64>(cB); }, nop);
        asm volatile("bar.sync 5, 256;" ::: "memory");
        auto stage = [&](int i) {
          stsm4t(a0 + i * 1024, pack_bf16(cB[8 * i] - cB[34 + 8 * i], cB[8 * i + 1] - cB[35 + 8 * i]),
                 pack_bf16(cB[32 + 8 * i] + cB[8 * i + 2], cB[33 + 8 * i] + cB[8 * i + 3]),
                 pack_bf16(cB[8 * i + 4] - cB[38 + 8 * i], cB[8 * i + 5] - cB[39 + 8 * i]),
                 pack_bf16(cB[36 + 8 * i] + cB[8 * i + 6], cB[37 + 8 * i] + cB[8 * i + 7]));
          if (j == 0 && w == 0) {
            const uint32_t a1 = r ? sb + OFF_SP + 1024 : sb + OFF_SP + wg * 512 + (m & 1) * 256 + (m >> 1) * 128;
#pragma unroll
            for (int n = 2 * i; n < 2 * i + 2; n++)
              asm volatile("stmatrix.sync.aligned.m8n8.x4.shared.b16 [%0], {%1,%2,%3,%4};" ::"r"(a1 + ((n ^ (kr + (m >> 1)) ^ r) << 4)),
                           "r"(pack_bf16(cB[4 * n], cB[4 * n + 1])), "r"(pack_bf16(cB[4 * n + 2], cB[4 * n + 3])),
                           "r"(pack_bf16(cB[32 + 4 * n], cB[33 + 4 * n])), "r"(pack_bf16(cB[34 + 4 * n], cB[35 + 4 * n])) : "memory");
          }
        };
        auto publish = [&] {
          asm volatile("fence.proxy.async.shared::cta;" ::: "memory");
          __syncwarp();
          mbar_arrive_if(lane == 0, bars + 8 * (B_XS + wg));
          if (tid == 0) PROF_EV(3);
        };
        stage(0);
        ffn_step(IC<1>(), IC<FSPLIT>(), cA, 6, 5, nop, nop);
        stage(1);
        ffn_step(IC<1>(), IC<FSPLIT>(), cA, 7, 6, nop, nop);
        stage(2);
        ffn_step(IC<1>(), IC<2>(), cA, 8, 7, [&] { stage(3); }, nop);
        publish();
      }
      float g0 = 0.f, g1 = 0.f;
      uint32_t tag = 0;
      uint32_t ob[2] = {0, 0};
      auto glu = [&](auto& acc, int half, int ho, int i0, int i1) {
#pragma unroll
        for (int i = i0; i < i1; i++)
          asm volatile("{\n.reg .b32 a, b;\ncvt.rn.relu.bf16x2.f32 a, %2, %1;\ncvt.rn.bf16x2.f32 b, %4, %3;\nmul.rn.bf16x2 a, a, b;\nmul.rn.bf16x2 %0, a, %5;\n}"
                       : "=r"(h[ho + i]) : "f"(acc[2 * i]), "f"(acc[2 * i + 1]), "f"(acc[half + 2 * i]), "f"(acc[half + 1 + 2 * i]), "r"(ob[i & 1]) : "memory");
      };
      ffn_step(IC<2>(), IC<1>(), cB, 9, zero, nop, nop);
#pragma unroll 1
      for (int kb = 1; kb < 8; kb++)
        ffn_step(IC<1>(), IC<FSPLIT>(), cB, 9 + kb, kb, nop, [&] {
          if (kb == 4 + 2 * wg) {
            mbar_wait(bars + 8 * B_G, 0);
            const uint32_t gb0 = *(const uint32_t*)(smem + OFF_G + (wg * 64 + w * 16 + g) * 4), gb1 = *(const uint32_t*)(smem + OFF_G + (wg * 64 + w * 16 + g + 8) * 4);
            tag = gb0 & 1; g0 = __uint_as_float(gb0 & ~1u); g1 = __uint_as_float(gb1 & ~1u);
            ob[0] = pack_bf16(1.0f - g0, 1.0f - g0); ob[1] = pack_bf16(1.0f - g1, 1.0f - g1);
            glu(cA, 32, 0, 0, 16);
          }
        });
      if (tid == 0) { PROF_EV(4); PROF_CK(43); }
      auto m_step = [&](auto first, int i) {
        acquire(17 + i);
        wg_fence();
        const uint64_t dx = d128(dX + i * 2048), dm = d64(dN + RING + rslot(17 + i) * 1024);
        mma_ss64<0, 1, decltype(first)::value>(ct, dx, dm);
#pragma unroll
        for (int k = 1; k < MSPLIT; k++) mma_ss64<0, 1, 1>(ct, dx + ((k >> 2) * 1024 + (k & 3) * 2), dm + k * 64);
        wg_commit();
        wg_wait<1>();
        freeP(17 + i);
        wg_fence();
#pragma unroll
        for (int k = MSPLIT; k < 8; k++) mma_ss64<0, 1, 1>(ct, dx + ((k >> 2) * 1024 + (k & 3) * 2), dm + k * 64);
        wg_commit();
      };
      m_step(IC<0>(), 0);
#pragma unroll 1
      for (int i = 1; i < 5; i++) {
        if (i == 1 + 2 * wg) glu(cB, 32, 16, 0, 16);
        if (i < 4) m_step(IC<1>(), i);
      }
      if (tid == 0) { PROF_EV(5); PROF_CK(44); }
      ffn_step(IC<0>(), IC<1>(), cC, 21, 0, nop, nop);
#pragma unroll 1
      for (int kb = 1; kb < 8; kb++)
        ffn_step(IC<1>(), IC<FSPLIT>(), cC, 21 + kb, kb, [&] { mbar_arrive_if(elect && !(kb & 1), bars + 8 * (B_ET + (kb >> 1) - 1)); }, [&] {
          if (kb == 1 + wg) glu(ct, 16, 48, 0, 8);
        });

      auto twait = [&](uint32_t bar, uint32_t par, int) { mbar_wait(bar, par); };
      auto tr = [] {};
      const int fo = warp * 128 + lane;
      auto fetch = [&](uint4 (&pv)[4], int z) {
        twait(bars + 8 * (z < 4 ? B_Z + 2 * z + wg : B_HP + z - 4), 0, 8 + z);
        const uint8_t* src = smem + (z < 5 ? OFF_Z + z * U : (z - 5) * U) + fo * 16;
#pragma unroll
        for (int i = 0; i < 4; i++) pv[i] = *(const uint4*)(src + i * 512);
      };
      auto check = [&](uint4 (&pv)[4], int z) {
        const uint32_t t0 = (uint32_t)clock();
        while (__any_sync(0xffffffffu, ((pv[0].x ^ tag) | (pv[1].x ^ tag) | (pv[2].x ^ tag) | (pv[3].x ^ tag)) & 1)) {
#pragma unroll
          for (int i = 0; i < 4; i++) pv[i] = ld_x4(ws->part + (size_t)((rb * 8 + j) * 3 + z - 4) * 1024 + fo + i * 32);
          spin_guard(t0);
        }
#pragma unroll
        for (int i = 0; i < 4; i++) pv[i].x &= ~1u;
      };
      const uint32_t peerZ = mapa(sb + OFF_Z + fo * 16, rank ^ 1), peerB = mapa(bars + 8 * (B_Z + wg), rank ^ 1);
      auto tile_mma = [&](auto off, int t, int k0, int k1, int init) {
        constexpr int O = decltype(off)::value;
        const uint64_t db = d128(dN + (t & 3) * (TB >> 4)), dw = db + rank * 256, dm = db + (rank ? 0 : 1536);
#pragma unroll
        for (int k = k0; k < k1; k++) {
          if (k == 0) mma_rs64<O, 1, 2>(ct, h[0], h[1], h[2], h[3], dw, init);
          else if (k < 14) mma_rs64<O, 1, 1>(ct, h[4 * k], h[4 * k + 1], h[4 * k + 2], h[4 * k + 3], k < 12 ? dw + k * 128 : dm + (k - 12) * 128);
          else mma_rs64<O, 1, 1>(ct, yf[4 * k - 56], yf[4 * k - 55], yf[4 * k - 54], yf[4 * k - 53], db + k * 128);
        }
      };
      auto tile = [&](auto off, int t) {
        constexpr int P = 32 - decltype(off)::value;
        const bool grid = t >= 4 && t < 7, pre = t != 1 && t != 5;
        const int zo = grid ? t - 4 : t == 7 ? 3 : t - 1, z = t - 2;
        const int owner = rb * 8 + 2 * ((q4 + zo + 1) & 3) + rank;
        uint4* dst = ws->part + (size_t)(owner * 3 + zo) * 1024 + fo;
        const uint32_t src = sb + (z < 5 ? OFF_Z + z * U : (z - 5) * U) + fo * 16;
        twait(bars + 8 * (B_FT + (t & 3)), t >> 2, t);
        wg_fence();
        tile_mma(off, t, 0, TH, t >= 3 && t != 6);
        wg_commit();
        wg_wait<1>();
        mbar_arrive_if(elect && t < 6, bars + 8 * (B_ET + t - 1));
        if (t == 1) twait(bars + 8 * B_RDY, 0, 15);
        fence_regs<P, 32>(ct);
        uint32_t pk[16];
#pragma unroll
        for (int i = 0; i < 16; i++) pk[i] = pack_bf16(ct[P + 2 * i], ct[P + 2 * i + 1]);
        wg_fence();
#pragma unroll
        for (int i = 0; i < 4; i++) {
          asm volatile(
              "{\n.reg .pred p;\nsetp.ne.b32 p, %7, 0;\n@p st.relaxed.gpu.global.v4.u32 [%0], {%3,%4,%5,%6};\n"
              "@!p st.async.weak.shared::cluster.mbarrier::complete_tx::bytes.v4.b32 [%1], {%3,%4,%5,%6}, [%2];\n}" ::"l"(dst + i * 32),
              "r"(peerZ + zo * U + i * 512), "r"(peerB + 16 * zo), "r"((pk[4 * i] & ~(uint32_t)grid) | (tag & grid)), "r"(pk[4 * i + 1]), "r"(pk[4 * i + 2]),
              "r"(pk[4 * i + 3]), "r"((int)grid) : "memory");
          if (i == 3) hint_add_if(grid && lane == 0, &ws->cntP[32 * owner + zo]);
          tile_mma(off, t, TH + 2 * i, TH + 2 * i + 2, 0);
        }
        wg_commit();
        if (pre) twait(bars + 8 * (z < 4 ? B_Z + 2 * z + wg : B_HP + z - 4), 0, 8 + z);
        wg_fence();
        uint4 pv[4];
#pragma unroll
        for (int i = 0; i < 4; i++) {
          asm volatile("{\n.reg .pred p;\nsetp.ne.b32 p, %5, 0;\n@p ld.shared.v4.u32 {%0,%1,%2,%3}, [%4];\n}"
                       : "=r"(pv[i].x), "=r"(pv[i].y), "=r"(pv[i].z), "=r"(pv[i].w) : "r"(src + i * 512), "r"((int)pre) : "memory");
          tile_mma(off, t, TH + 8 + i, i < 3 ? TH + 9 + i : 18, 0);
        }
        wg_commit();
        if (pre) {
          if (z >= 4) check(pv, z);
#pragma unroll
          for (int i = 0; i < 4; i++) {
            const uint32_t a[4] = {pv[i].x, pv[i].y, pv[i].z, pv[i].w};
#pragma unroll
            for (int e = 0; e < 4; e++) { ct[P + 8 * i + 2 * e] = bf_lo(a[e]); ct[P + 8 * i + 2 * e + 1] = bf_hi(a[e]); }
          }
        }
      };
      asm volatile("barrier.cluster.wait.aligned;" ::: "memory");
      twait(bars + 8 * B_FT, 0, 0);
      wg_fence();
      tile_mma(IC<0>(), 0, 0, 5, zero);
      wg_commit();
      wg_wait<1>();
      mbar_arrive_if(elect, bars + 8 * (B_ET + 3));
      glu(cC, 32, 32, 0, 8);
      waitA(29 + wg);
      wg_fence();
      tile_mma(IC<0>(), 0, 5, 8, 0);
      tile_mma(IC<0>(), 0, 12, 14, 0);
      wg_commit();
      glu(cC, 32, 32, 8, 16);
      if (tid == 0) PROF_EV(6);
      if (tid == 128) PROF_EV(27);
      mbar_wait(bars + 8 * (j == 0 ? B_T : B_TL), 0);
      if (tid == 0) { PROF_EV(7); PROF_CK(45); }
      wg_fence();
      {
        const uint64_t dt = d128(dN + (OFF_T >> 4) + wg * 512), de = d128(dK + RING + (1 + wg) * 1024);
        mma_ss64<0, 1, 0>(ci, de, dt);
        mma_ss64<32, 1, 0>(ci, de + 512, dt);
#pragma unroll
        for (int k = 1; k < 4; k++) {
          mma_ss64<0, 1, 1>(ci, de + k * 2, dt + k * 128);
          mma_ss64<32, 1, 1>(ci, de + (512 + k * 2), dt + k * 128);
        }
        wg_commit();
      }
      tile_mma(IC<0>(), 0, 8, 12, 0);
      wg_commit();
      wg_wait<1>();
      if (elect) asm volatile("mbarrier.arrive.shared::cluster.b64 _, [%0];" ::"r"(mapa(bars + 8 * B_RDY, rank ^ 1)) : "memory");
      mbar_arrive_if(elect, bars + 8 * (B_PZ + 1));
      fence_regs<0, 64>(ci);
#pragma unroll
      for (int i = 0; i < 16; i++) {
        const float gg = ((i & 1) ? g1 : g0) * (2.0f / (2048.0f * 512.0f));
        if (i & 2) yf[i] = pack_pin((ci[2 * i] - ci[28 + 2 * i]) * gg, (ci[2 * i + 1] - ci[29 + 2 * i]) * gg);
        else yf[i] = pack_pin((ci[2 * i] + ci[36 + 2 * i]) * gg, (ci[2 * i + 1] + ci[37 + 2 * i]) * gg);
      }
      wg_fence();
      tile_mma(IC<0>(), 0, 14, 18, 0);
      wg_commit();
      if (tid == 0) PROF_EV(8);
      if (tid == 128) PROF_EV(28);
#pragma unroll 1
      for (int t = 1;; t += 2) {
        tile(IC<32>(), t);
        if (t == 7) break;
        tile(IC<0>(), t + 1);
      }
      if (tid == 0) { PROF_EV(9); PROF_CK(46); }
      if (tid == 128) PROF_EV(29);
      {
        float (&sum)[64] = ct;
        uint4 p2[4], p3[4];
        fetch(p3, 3);
        if (tid == 0) PROF_EV(25);
        fetch(p2, 6);
        if (tid == 0) PROF_EV(24);
        check(p2, 6);
#pragma unroll
        for (int i = 0; i < 4; i++) {
          const uint32_t b[4] = {p2[i].x, p2[i].y, p2[i].z, p2[i].w}, c[4] = {p3[i].x, p3[i].y, p3[i].z, p3[i].w};
#pragma unroll
          for (int e = 0; e < 4; e++) {
            sum[8 * i + 2 * e] += bf_lo(c[e]) + bf_lo(b[e]);
            sum[8 * i + 2 * e + 1] += bf_hi(c[e]) + bf_hi(b[e]);
          }
        }
        if (tid == 0) PROF_EV(14);
        wg_wait<0>();
        fence_regs<32, 32>(ct);
#pragma unroll
        for (int i = 0; i < 32; i++) sum[i] += ct[32 + i];
        const uint32_t stg = sb + OFF_T + warp * 2048;
        const int mr = (lane & 7) + ((lane >> 3) & 1) * 8, mc = lane >> 4;
#pragma unroll
        for (int i = 0; i < 4; i++) {
          const uint32_t a = stg + mr * 128 + (((2 * i + mc) ^ (mr & 7)) << 4);
          asm volatile("stmatrix.sync.aligned.m8n8.x4.shared.b16 [%0], {%1,%2,%3,%4};" ::"r"(a), "r"(pack_bf16(sum[8 * i], sum[8 * i + 1])),
                       "r"(pack_bf16(sum[8 * i + 2], sum[8 * i + 3])), "r"(pack_bf16(sum[8 * i + 4], sum[8 * i + 5])),
                       "r"(pack_bf16(sum[8 * i + 6], sum[8 * i + 7])) : "memory");
        }
        asm volatile("fence.proxy.async.shared::cta;" ::: "memory");
        __syncwarp();
        if (elect_one()) {
          asm volatile("cp.async.bulk.tensor.3d.global.shared::cta.bulk_group [%0, {%2, %3, %4}], [%1];" ::"l"(&maps.o), "r"(stg), "r"(64 * j),
                       "r"(16 * w), "r"(2 * rb + wg) : "memory");
          asm volatile("cp.async.bulk.commit_group;\ncp.async.bulk.wait_group.read 0;" ::: "memory");
        }
      }
      if (tid == 0) { PROF_EV(15); PROF_CK(41); }
      if (tid == 128) PROF_EV(30);
    }
  } else if (warp < 12) {
    asm volatile("setmaxnreg.dec.sync.aligned.u32 104;");
    asm volatile("barrier.cluster.arrive.relaxed.aligned;" ::: "memory");
    const int t = tid - 256, w = warp - 8;
    const uint32_t ep = ld_x1(&ws->epoch[blockIdx.x * 8]);
    const uint32_t tag = (ep + 1) & 1;
    auto w_issue = [&](const CUtensorMap* m) {

      if (elect_one()) { mbar_expect_tx(bars + 8 * (B_WR + w), 3072); tma4d(sb + OFF_T + w * 3072, m, bars + 8 * (B_WR + w), 16 * kg, 0, 2 * w, tn); }

          __syncwarp();
    };
    auto gate_rows = [&] {
      const int r = 16 * j + 4 * w + (lane >> 3);
      const uint4* pg = (const uint4*)gate_w + (lane & 7);
      {
        float a = 0.f;
        asm volatile("bar.sync 4, 256;" ::: "memory");
#pragma unroll 1
        for (int hf = 0; hf < 2; hf++) {
          uint4 v[4], u[4];
#pragma unroll
          for (int kb = 0; kb < 4; kb++) v[kb] = __ldg(pg + (4 * hf + kb) * 8);
          mbar_wait(bars + 8 * (B_FE + 1 + 2 * hf), 0);
          if (hf) w_issue(&maps.wr);
#pragma unroll
          for (int kb = 0; kb < 4; kb++) u[kb] = *(const uint4*)(smem + (4 * hf + kb) * U + r * 128 + (((lane ^ r) & 7) << 4));
#pragma unroll
          for (int kb = 0; kb < 4; kb++) {
            a = fmaf(bf_lo(u[kb].x), bf_lo(v[kb].x), a); a = fmaf(bf_hi(u[kb].x), bf_hi(v[kb].x), a);
            a = fmaf(bf_lo(u[kb].y), bf_lo(v[kb].y), a); a = fmaf(bf_hi(u[kb].y), bf_hi(v[kb].y), a);
            a = fmaf(bf_lo(u[kb].z), bf_lo(v[kb].z), a); a = fmaf(bf_hi(u[kb].z), bf_hi(v[kb].z), a);
            a = fmaf(bf_lo(u[kb].w), bf_lo(v[kb].w), a); a = fmaf(bf_hi(u[kb].w), bf_hi(v[kb].w), a);
          }
        }
#pragma unroll
        for (int o = 4; o; o >>= 1) a += __shfl_xor_sync(0xffffffffu, a, o);
        if ((lane & 7) == 0)
          asm volatile("st.relaxed.gpu.global.f32 [%0], %1;" ::"l"(ws->gate + rb * 128 + r), "f"(tagf(__fdividef(1.0f, 1.0f + __expf(-a)), tag)) : "memory");
        if (t == 0) PROF_EV(18);
      }
    };
    {
      const int g = lane >> 2, q = lane & 3;
      uint32_t wf[32];
      if (!helper) {
        gate_rows();
        const uint32_t wa = sb + OFF_T + w * (3072 + 4) + q * 48 + g * 2;
#pragma unroll 1
        for (int ri = 0; ri < 2; ri++) {
          mbar_wait(bars + 8 * (B_WR + w), ri);
#pragma unroll
          for (int n2 = 0; n2 < 32 / WB; n2++) {
            uint32_t v[WB];
#pragma unroll
            for (int i = 0; i < WB; i++) {
              const int e = n2 * WB + i;
              asm volatile("ld.shared.u16 %0, [%1];" : "=r"(v[i]) : "r"(wa + ((e >> 1) & 7) * 192 + (e & 1) * (1536 + 2) + (e >> 4) * 16) : "memory");
            }
#pragma unroll
            for (int i = 0; i < WB; i++) wf[n2 * WB + i] = __byte_perm(wf[n2 * WB + i], v[i], 0x5432);
            if (WSLEEP) { asm volatile("nanosleep.u32 %0;" ::"r"(WSLEEP + (v[WB - 1] >> 16)) : "memory"); }
          }
          __syncwarp();
          if (ri == 0) w_issue(&maps.wi);
        }
        asm volatile("bar.sync 1, 128;" ::: "memory");
        if (t == 0) PROF_EV(11);
      } else {
        asm volatile("bar.sync 4, 256;" ::: "memory");
        hint_wait(&ws->cntW[0], (ep + 1) * 128u);
        const uint32_t t0 = (uint32_t)clock();
#pragma unroll 1
        for (;;) {
          uint32_t bad = 0;
#pragma unroll
          for (int i = 0; i < 32; i++) {
            const float2 v = ld_x2((const float2*)ws->Wh + (i >> 4) * 2048 + 16 * w + g + 8 * (i & 1) + 64 * q + ((i >> 1) & 7) * 256);
            wf[i] = __float_as_uint(v.x); bad |= __float_as_uint(v.y) ^ tag;
          }
          if (!__any_sync(0xffffffffu, bad & 1)) break;
          spin_guard(t0);
        }
        if (t == 0) PROF_EV(11);
      }
      if (w == 0 && elect_one()) { mbar_expect_tx(bars + 8 * B_W, 8192); bulk_load(sb + OFF_D, dtab, 8192, bars + 8 * B_W); }
      mbar_wait(bars + 8 * B_W, 0);
      mbar_wait(bars + 8 * B_HX, 0);
      if (t == 0) PROF_EV(12);
      const uint32_t dd = (sb & 0x3FFFF) >> 4;
      const uint64_t dF = d128((dd + (OFF_D >> 4)) | (512u << 16)), dI = d128((dd + (OFF_D >> 4)) | (1u << 16)), dA = d128((dd + (OFF_XB >> 4)) | (512u << 16));
      float az[32];
      const int zero = blockIdx.x >> 16;
      uint32_t pf[32];
#pragma unroll
      for (int mt = 0; mt < 2; mt++) {
        wg_fence();
        if (mt == 0) mma_ss64<0, 3, 0>(az, dA, dF);
        else mma_ss64<0, 3, 2>(az, dA + 512, dF, zero);
#pragma unroll
        for (int k = 1; k < 4; k++) mma_ss64<0, 3, 1>(az, dA + (mt * 512 + k * 128), dF + k * 128);
        wg_commit();
        wg_wait<0>();
        fence_regs<0, 32>(az);
#pragma unroll
        for (int i = 0; i < 16; i++) {
          const float wr = bf_lo(wf[16 * mt + i]), wi = bf_hi(wf[16 * mt + i]);
          pf[16 * mt + i] = pack_pin(fmaf(az[2 * i], wr, -az[2 * i + 1] * wi), fmaf(az[2 * i], wi, az[2 * i + 1] * wr));
        }
      }
      if (t == 0) PROF_EV(16);
      {
        const int m = lane >> 3, r = lane & 7;
        const int sl = 2 * (m >> 1) + ((r >> 1) & 1) + 4 * (r >> 2);
        const uint32_t a0 = sb + OFF_XB + (2 * w + (m & 1)) * 2048 + sl * 64;
        uint32_t pk[16];
#pragma unroll
        for (int mt = 0; mt < 3; mt++) {
          if (mt < 2) {
            wg_fence();
            mma_rs64<0, 0, 2>(az, pf[16 * mt], pf[16 * mt + 1], pf[16 * mt + 2], pf[16 * mt + 3], dI, mt ? (int)helper : zero);
#pragma unroll
            for (int k = 1; k < 4; k++) mma_rs64<0, 0, 1>(az, pf[16 * mt + 4 * k], pf[16 * mt + 4 * k + 1], pf[16 * mt + 4 * k + 2], pf[16 * mt + 4 * k + 3], dI + k * 2);
            wg_commit();
          }
          if (mt > 0 && !helper) {
#pragma unroll
            for (int i = 0; i < 4; i++) stsm4t(a0 + ((((mt - 1) * 2 + (r & 1)) ^ (sl >> 1)) << 4) + i * 512, pk[4 * i], pk[4 * i + 1], pk[4 * i + 2], pk[4 * i + 3]);
          }
          if (mt < 2) {
            wg_wait<0>();
            fence_regs<0, 32>(az);
#pragma unroll
            for (int i = 0; i < 16; i++) pk[i] = pack_pin(az[2 * i], az[2 * i + 1]);
          }
        }
      }
      if (helper) {
#pragma unroll
        for (int i = 0; i < 16; i++) {
          const int n = i >> 1, s0 = 8 * (n >> 1) + 2 * (n & 1) + (q & 1) + 4 * (q >> 1);
          if ((n & 1) == (int)(blockIdx.x & 1)) st_u2(ws->Ts + s0 * 64 + 16 * w + g + 8 * (i & 1), pack_bf16(az[2 * i], az[2 * i + 1]), tag);
        }
        __syncwarp();
        hint_add_if(lane == 0, &ws->cntH[0]);
        if (t == 0) { ws->epoch[blockIdx.x * 8] = ep + 1; PROF_EV(13); }
      } else {
        asm volatile("fence.proxy.async.shared::cta;" ::: "memory");
        __syncwarp();
        if (elect_one()) {
          if (t == 0) PROF_EV(17);
          if (SPACE) __nanosleep(SPACE * w);
          asm volatile("cp.async.bulk.tensor.3d.global.shared::cta.bulk_group [%0, {%2, %3, %4}], [%1];" ::"l"(&maps.ts), "r"(sb + OFF_XB + w * 4096),
                       "r"(32 * kg), "r"(0), "r"(8 * tn + 2 * w) : "memory");
          bulk_done_signal(&ws->cntT[32 * j]);
          if (t == 96) PROF_EV(13);
        }
        __syncwarp();
        if (j == 0) {
          hint_wait(&ws->cntH[0], (ep + 1) * 8u);
          const uint32_t t0 = (uint32_t)clock();
          float2 v;
          do { v = ld_x2((const float2*)ws->Ts + 2 * rb * 64 + t); spin_guard(t0); } while (__any_sync(0xffffffffu, (__float_as_uint(v.y) ^ tag) & 1));
          mbar_wait(bars + 8 * B_TL, 0);
          const uint32_t u = __float_as_uint(v.x);
          *(uint16_t*)(smem + OFF_T + t * 128 + ((t & 7) << 4)) = (uint16_t)u;
          *(uint16_t*)(smem + OFF_T + t * 128 + (((t & 7) ^ 1) << 4)) = (uint16_t)(u >> 16);
          asm volatile("fence.proxy.async.shared::cta;" ::: "memory");
          __syncwarp();
          mbar_arrive_if(lane == 0, bars + 8 * B_T);
        }
      }
    }
  } else {
    asm volatile("setmaxnreg.dec.sync.aligned.u32 24;");
    auto xf_load = [&](int q) {
      const uint32_t fb = bars + 8 * (B_FX + q);
      mbar_expect_tx(fb, U + 8192);
      tma3d(sb + q * U, &maps.x, fb, 64 * q, 0, 2 * rb);
      if (q >= 4) mbar_wait(bars + 8 * (B_FE + ((q - 4) >> 1)), 0);
      tma2d(sb + OFF_XB + (q & 3) * 8192, &maps.ft, fb, 64 * q, 64 * j);
    };
    if (elect_one()) {
      if (warp == 14) {
#pragma unroll
        for (int i = 0; i < B_FT; i++) mbar_init(bars + 8 * i, 1);
        asm volatile("fence.mbarrier_init.release.cluster;" ::: "memory");
        if (!helper) {
#pragma unroll 1
          for (int n = 0; n < 2; n++) {
            const uint32_t fb = bars + 8 * (B_FA + n);
            xf_load(2 * n); xf_load(2 * n + 1);
            mbar_expect_tx(fb, U);
            tma2d(sb + OFF_RING + n * U, &maps.g64, fb, f_full, 64 * n);
            tma2d(sb + OFF_RING + n * U + 8192, &maps.u64, fb, f_full, 64 * n);
          }
        }
      } else if (warp == 15) {
#pragma unroll
        for (int i = B_FT; i < NBAR; i++) mbar_init(bars + 8 * i, i < B_EA ? 1 : i < B_T ? 2 : 4);
#pragma unroll
        for (int i = 0; i < 8; i++) mbar_expect_tx(bars + 8 * (B_Z + i), U / 2);
        asm volatile("fence.mbarrier_init.release.cluster;" ::: "memory");
        asm volatile("fence.proxy.async.shared::cta;" ::: "memory");
      } else if (warp == 13 && !PF0) {
#pragma unroll
        for (int i = 1; i < 4; i++) asm volatile("prefetch.tensormap [%0];" ::"l"((const char*)&maps + i * 128) : "memory");
      }
    }
    __syncwarp();
    asm volatile("bar.arrive 0, 384;" ::: "memory");
    asm volatile("bar.arrive 4, 256;" ::: "memory");
    __syncwarp();
    asm volatile("barrier.cluster.arrive.relaxed.aligned;" ::: "memory");
    asm volatile("bar.sync 3, 128;" ::: "memory");
    if (warp == 15 && !helper) {
        mbar_wait(bars + 8 * B_FE, 0);
        const uint32_t tag = (ld_x1(&ws->epoch[blockIdx.x * 8]) + 1) & 1;
        const int c = lane >> 4, jj = 16 * blockIdx.x + (lane & 15), jm = (2048 - jj) & 2047;
        const unsigned short* pr = (const unsigned short*)w_r + 256 * c;
        const unsigned short* pi = (const unsigned short*)w_i + 256 * c;
        const float wr = 0.25f * (bf_lo(__ldg(pr + jj * 257)) + bf_lo(__ldg(pr + jm * 257)));
        const float wi = 0.25f * (bf_lo(__ldg(pi + jj * 257)) - bf_lo(__ldg(pi + jm * 257)));
        st_u2(ws->Wh + c * 2048 + jj, c ? pack_bf16(-wi, wr) : pack_bf16(wr, wi), tag);
        __syncwarp();
        hint_add_if(lane == 0, &ws->cntW[0]);
        mbar_wait(bars + 8 * B_XS, 0);
        const uint32_t t0 = (uint32_t)clock();
        uint4 v;
        do { v = ld_x4(ws->gate + rb * 128 + 4 * lane); spin_guard(t0); } while (__any_sync(0xffffffffu, ((v.x ^ tag) | (v.y ^ tag) | (v.z ^ tag) | (v.w ^ tag)) & 1));
        *(uint4*)(smem + OFF_G + lane * 16) = v;
        __syncwarp();
        mbar_arrive_if(lane < 4, bars + 8 * B_G);
      }
    if ((!helper || warp == 15) && elect_one()) {
      if (warp < 14) {
        const int p = warp - 12;
#pragma unroll 1
        for (int i = 4 + p; i < 14; i += 2) asm volatile("prefetch.tensormap [%0];" ::"l"((const char*)&maps + i * 128) : "memory");
#pragma unroll 1
        for (int n = 2; n < 31; n++) {
          const bool table = n == 4 || n >= 29;
          const bool half = n >= 17 && n < 21;
          const int q = n < 4 ? n : n < 17 ? n - 1 : n - 5;
          const CUtensorMap* m = table ? &maps.e : half ? &maps.g32 + p : &maps.g64 + p;
          const int c0 = table ? 0 : half ? f_half : f_full + 64 * (q >> 3);
          const int c1 = table ? (2 * rb + ((n & 1) ^ 1)) * 128 + 64 * p : half ? 128 * (n - 17) : 64 * (q & 7);
          const uint32_t fb = bars + 8 * (B_FA + (n & 3)), dst = sb + OFF_RING + (n & 3) * U + p * 8192;
          if (n < 4) mbar_wait(bars + 8 * (B_FE + n - 2), 0);
          else mbar_wait(bars + 8 * (B_EA + (n & 3)), ((n >> 2) & 1) ^ 1);
          tma2d(dst, m, fb, c0, c1);
          if (p == 0) mbar_expect_tx(fb, U);
        }
      } else if (warp == 15) {
        const unsigned ep1 = ld_x1(&ws->epoch[blockIdx.x * 8]) + 1;
        flag_wait(&ws->cntX[helper ? 0 : 32 * j], ep1 * 16u);
        PROF_EV(22);
        mbar_expect_tx(bars + 8 * B_HX, U);
        bulk_load(sb + OFF_XB, ws->X + (size_t)(helper ? 128 : kg * 8 + tn) * 8192, U, bars + 8 * B_HX);
        if (!helper) {
          flag_wait(&ws->cntT[32 * j], ep1 * 64u);
          PROF_EV(23);
          mbar_expect_tx(bars + 8 * B_TL, U);
          tma3d(sb + OFF_T, &maps.t, bars + 8 * B_TL, 64 * j, 0, 2 * rb);
#pragma unroll 1
          for (int i = 0; i < 3; i++) {
            flag_wait(&ws->cntP[32 * (rb * 8 + j) + i], ep1 * 8u);
            mbar_wait(bars + 8 * (B_PZ + (i == 0)), 0);
            if (i == 2) PROF_EV(26);
            mbar_expect_tx(bars + 8 * (B_HP + i), U);
            bulk_load(sb + (i ? (i - 1) * U : OFF_T), ws->part + (size_t)((rb * 8 + j) * 3 + i) * 1024, U, bars + 8 * (B_HP + i));
          }
          ws->epoch[blockIdx.x * 8] = ep1;
        }
      } else {
#pragma unroll 1
        for (int q = 4; q < 8; q++) xf_load(q);
        mbar_wait(bars + 8 * (B_FE + 2), 0);
        mbar_expect_tx(bars + 8 * B_E0, U);
        tma2d(sb + OFF_XB, &maps.e, bars + 8 * B_E0, 0, 2 * rb * 128);
        tma2d(sb + OFF_XB + 8192, &maps.e, bars + 8 * B_E0, 0, 2 * rb * 128 + 64);
#pragma unroll 1
        for (int h2 = 0; h2 < 2; h2++) {
          const int s0 = 2 * rb + h2, sg = (s0 & ~6) | ((s0 & 2) << 1) | ((s0 & 4) >> 1);
          mbar_wait(bars + 8 * (B_XS + h2), 0);
#pragma unroll 1
          for (int c = 0; c < 2; c++) {
            asm volatile("cp.async.bulk.tensor.4d.global.shared::cta.bulk_group [%0, {%2, %3, %4, %5}], [%1];" ::"l"(&maps.xs),
                         "r"(sb + OFF_XB + h2 * 8192 + c * 4096), "r"(0), "r"(sg), "r"(0), "r"(16 * j + 8 * c) : "memory");
            if (j == 0)
              asm volatile("cp.async.bulk.global.shared::cta.bulk_group [%0], [%1], 256;" ::"l"(ws->X + 128 * 8192 + c * 4096 + sg * 128),
                           "r"(sb + OFF_SP + h2 * 512 + c * 256) : "memory");
            if (SPACE && h2 + c < 2) __nanosleep(SPACE);
          }
        }
        bulk_done_signal(&ws->cntX[32 * j]);
        PROF_EV(20);
        if (rb < 8) asm volatile("cp.async.bulk.prefetch.tensor.2d.L2.global [%0, {%1, %2}];" ::"l"(&maps.g32 + (rb >> 2)), "r"(f_half), "r"(128 * (rb & 3)) : "memory");
        else asm volatile("cp.async.bulk.prefetch.tensor.2d.L2.global [%0, {%1, %2}];" ::"l"(&maps.d224), "r"(64 * (rb - 8)), "r"(224 * j) : "memory");
#pragma unroll 1
        for (int t = 0; t < 8; t++) {
          const int i = t < 3 ? t + 1 : t < 6 ? t - 2 : 0;
          const int col = 64 * (2 * ((q4 + i) & 3) + ((t < 3 || t == 6) ? 1 - rank : rank));
          const uint32_t fb = bars + 8 * (B_FT + (t & 3)), dst = sb + (t & 3) * TB;
          mbar_wait(bars + 8 * (B_ET + (t == 2 ? 3 : t & 3)), t >> 2);
          mbar_expect_tx(fb, TB);
          tma2d(dst, &maps.d224, fb, col, 224 * j);
          if (t < 2) mbar_wait(bars + 8 * (B_ET + t + 1), 0);
          tma2d(dst + 28672, &maps.ft, fb, col, 64 * j);
        }
      }
    }
  }
}

typedef CUresult (*EncodeFn)(CUtensorMap*, CUtensorMapDataType, cuuint32_t, void*, const cuuint64_t*, const cuuint64_t*, const cuuint32_t*,
                             const cuuint32_t*, CUtensorMapInterleave, CUtensorMapSwizzle, CUtensorMapL2promotion, CUtensorMapFloatOOBfill);

static void encode(EncodeFn f, CUtensorMap* m, const void* base, int rank, const cuuint64_t* dims, const cuuint64_t* strides, const cuuint32_t* box,
                   CUtensorMapSwizzle sw) {
  cuuint32_t es[5] = {1, 1, 1, 1, 1};
  f(m, CU_TENSOR_MAP_DATA_TYPE_BFLOAT16, rank, (void*)base, dims, strides, box, es, CU_TENSOR_MAP_INTERLEAVE_NONE, sw,
    CU_TENSOR_MAP_L2_PROMOTION_L2_128B, CU_TENSOR_MAP_FLOAT_OOB_FILL_NONE);
}

extern "C" void kernel_launch(void* const* d_in, const int* in_sizes, int n_in, void* d_out, int out_size) {
  (void)in_sizes; (void)n_in; (void)out_size;
  const __nv_bfloat16* x = (const __nv_bfloat16*)d_in[0];
  const __nv_bfloat16* w_r = (const __nv_bfloat16*)d_in[1];
  const __nv_bfloat16* w_i = (const __nv_bfloat16*)d_in[2];
  const __nv_bfloat16* Wg = (const __nv_bfloat16*)d_in[4];
  const __nv_bfloat16* Wu = (const __nv_bfloat16*)d_in[5];
  const __nv_bfloat16* Wd = (const __nv_bfloat16*)d_in[6];
  const __nv_bfloat16* gw = (const __nv_bfloat16*)d_in[7];

  void* fp = nullptr; cudaDriverEntryPointQueryResult qr;
  cudaGetDriverEntryPoint("cuTensorMapEncodeTiled", &fp, cudaEnableDefault, &qr);
  EncodeFn enc = (EncodeFn)fp;
  void *pFT, *pET, *pDT, *pW;
  cudaGetSymbolAddress(&pDT, g_DT); cudaGetSymbolAddress(&pW, g_work);
  void *pX = ((Work*)pW)->X, *pT = ((Work*)pW)->T;
  cudaGetSymbolAddress(&pFT, g_FT); cudaGetSymbolAddress(&pET, g_ET);

  Maps mp;
  const CUtensorMapSwizzle S128 = CU_TENSOR_MAP_SWIZZLE_128B, S64 = CU_TENSOR_MAP_SWIZZLE_64B;
  { cuuint64_t d[3] = {512, 64, 32}, s[2] = {32768, 1024}; cuuint32_t b[3] = {64, 64, 2}, b2[3] = {64, 16, 1};
    encode(enc, &mp.x, x, 3, d, s, b, S128); encode(enc, &mp.o, d_out, 3, d, s, b2, S128); }
  { cuuint64_t d[2] = {512, 512}, s[1] = {1024}; cuuint32_t b[2] = {64, 64}; encode(enc, &mp.ft, pFT, 2, d, s, b, S128); }
  { cuuint64_t d[4] = {128, 32, 2, 129}, s[3] = {256, 8192, 16384}; cuuint32_t b[4] = {128, 1, 2, 8}; encode(enc, &mp.xs, pX, 4, d, s, b, CU_TENSOR_MAP_SWIZZLE_NONE); }
  { cuuint64_t d[3] = {512, 32, 64}, s[2] = {65536, 1024}; cuuint32_t b[3] = {32, 32, 2}; encode(enc, &mp.ts, pT, 3, d, s, b, S64); }
  { cuuint64_t d[3] = {512, 64, 32}, s[2] = {1024, 65536}; cuuint32_t b[3] = {64, 64, 2}; encode(enc, &mp.t, pT, 3, d, s, b, S128); }
  { cuuint64_t d[2] = {64, 4096}, s[1] = {128}; cuuint32_t b[2] = {64, 64}; encode(enc, &mp.e, pET, 2, d, s, b, S128); }
  { cuuint64_t d[2] = {1792, 512}, s[1] = {3584}; cuuint32_t b[2] = {64, 64}, b2[2] = {32, 128};
    encode(enc, &mp.g64, Wg, 2, d, s, b, S128); encode(enc, &mp.u64, Wu, 2, d, s, b, S128);
    encode(enc, &mp.g32, Wg, 2, d, s, b2, S64); encode(enc, &mp.u32, Wu, 2, d, s, b2, S64); }
  { cuuint64_t d[2] = {512, 1792}, s[1] = {1024}; cuuint32_t b[2] = {64, 224}; encode(enc, &mp.d224, Wd, 2, d, s, b, S128); }
  { cuuint64_t d[4] = {264, 32, 8, 8}, s[3] = {32896, 512, 4112}; cuuint32_t b[4] = {24, 32, 2, 1};
    encode(enc, &mp.wr, w_r, 4, d, s, b, CU_TENSOR_MAP_SWIZZLE_NONE); encode(enc, &mp.wi, w_i, 4, d, s, b, CU_TENSOR_MAP_SWIZZLE_NONE); }

  cudaFuncSetAttribute(fused_kernel, cudaFuncAttributeMaxDynamicSharedMemorySize, SMEM_BYTES);
  fused_kernel<<<NCTA, 512, SMEM_BYTES>>>((Work*)pW, (const uint16_t*)pDT, w_r, w_i, gw, x, (const uint16_t*)pFT, Wg, Wu, mp);
}
```

```cpp
#include <cuda_runtime.h>
#include <cuda_bf16.h>
#include <cuda.h>
#include <stdint.h>

namespace tbl {
constexpr double PI = 3.14159265358979323846264338327950288;
constexpr double sin_s(double x) { double t = x, s = x; for (int n = 1; n < 12; n++) { t *= -x * x / ((2 * n) * (2 * n + 1)); s += t; } return s; }
constexpr double cos_s(double x) { double t = 1, s = 1; for (int n = 1; n < 12; n++) { t *= -x * x / ((2 * n - 1) * (2 * n)); s += t; } return s; }
constexpr double cos2048(int m) {
  m &= 2047; if (m > 1024) m = 2048 - m;
  bool neg = false; if (m > 512) { m = 1024 - m; neg = true; }
  double v = (m <= 256) ? cos_s(2 * PI * m / 2048) : sin_s(2 * PI * (512 - m) / 2048);
  return neg ? -v : v;
}
constexpr uint16_t to_bf16(double v) {
  if (v == 0) return 0;
  uint16_t s = 0; if (v < 0) { s = 0x8000; v = -v; }
  int e = 0; while (v >= 2) { v /= 2; e++; } while (v < 1) { v *= 2; e--; }
  double m = (v - 1) * 128; int mi = (int)m; double fr = m - mi;
  if (fr > 0.5 || (fr == 0.5 && (mi & 1))) mi++;
  if (mi == 128) { mi = 0; e++; }
  return (uint16_t)(s | ((e + 127) << 7) | mi);
}
struct CosT { uint16_t v[2048]; constexpr CosT() : v() { for (int i = 0; i < 2048; i++) v[i] = to_bf16(cos2048(i)); } };
struct alignas(1024) FT {
  uint16_t v[512 * 512];
  constexpr FT() : v() {
    CosT c;
    for (int r = 0; r < 512; r++) {
      int k = (r >> 4) * 8 + (r & 7), e = (r >> 3) & 1;
      int mul = 4 * k, add = e ? 512 : 0;
      if (k == 0 && e == 1) { mul = 1024; add = 0; }
      for (int d = 0; d < 512; d++) v[r * 512 + d] = c.v[(d * mul + add) & 2047];
    }
  }
};
struct alignas(1024) ET {
  uint16_t v[2048 * 128];
  constexpr ET() : v() {
    CosT c;
    for (int s = 0; s < 2048; s++)
      for (int j = 0; j < 64; j++) {
        const int o = (s & 31) * 8192 + (s >> 5) * 64 + j;
        v[o] = c.v[(s * j) & 2047]; v[o + 4096] = c.v[(s * j + 512) & 2047];
      }
  }
};
struct alignas(1024) DT {
  uint16_t v[64 * 64];
  constexpr DT() : v() {
    CosT c;
    for (int r = 0; r < 64; r++)
      for (int n = 0; n < 64; n++) {
        const int sg = r >> 1, s0 = (sg & ~6) | ((sg & 2) << 1) | ((sg & 4) >> 1), e = r & 1, f = n & 1;
        const int m = 64 * s0 * (n >> 1) + (e == f ? 0 : e ? -512 : 512);
        v[r * 64 + (((n >> 3) ^ (r & 7)) << 3) + (n & 7)] = c.v[m & 2047];
      }
  }
};
}

__device__ constexpr tbl::FT g_FT = tbl::FT();
__device__ constexpr tbl::ET g_ET = tbl::ET();
__device__ constexpr tbl::DT g_DT = tbl::DT();

struct alignas(1024) Work {
  unsigned epoch[132 * 8];
  unsigned cntX[8 * 32], cntT[8 * 32], cntP[128 * 32], cntW[32], cntH[32];
  alignas(16) float gate[16 * 128];
  alignas(16) uint2 Wh[2 * 2048];
  alignas(16) uint2 Ts[32 * 64];
  alignas(1024) uint16_t X[129 * 8192];
  alignas(1024) uint16_t T[32 * 64 * 512];
  alignas(1024) uint4 part[128 * 3 * 1024];
};
__device__ Work g_work;
#define PROF_EV(i) do {} while (0)
#define PROF_CK(i) do {} while (0)

__device__ __forceinline__ uint32_t smem_u32(const void* p) { return (uint32_t)__cvta_generic_to_shared(p); }
__device__ __forceinline__ void mbar_init(uint32_t bar, uint32_t cnt) { asm volatile("mbarrier.init.shared::cta.b64 [%0], %1;" ::"r"(bar), "r"(cnt)); }
__device__ __forceinline__ void mbar_expect_tx(uint32_t bar, uint32_t bytes) { asm volatile("mbarrier.arrive.expect_tx.shared::cta.b64 _, [%0], %1;" ::"r"(bar), "r"(bytes) : "memory"); }
__device__ __forceinline__ void mbar_arrive(uint32_t bar) { asm volatile("mbarrier.arrive.shared::cta.b64 _, [%0];" ::"r"(bar) : "memory"); }
__device__ __forceinline__ bool elect_one() {
  uint32_t p;
  asm volatile("{\n.reg .pred p;\nelect.sync _|p, 0xffffffff;\nselp.u32 %0, 1, 0, p;\n}" : "=r"(p));
  return p;
}
__device__ __forceinline__ void mbar_arrive_if(bool p, uint32_t bar) {
  asm volatile("{\n.reg .pred p;\nsetp.ne.b32 p, %1, 0;\n@p mbarrier.arrive.shared::cta.b64 _, [%0];\n}" ::"r"(bar), "r"((int)p) : "memory");
}
__device__ __forceinline__ void hint_add_if(bool p, unsigned* a) {
  asm volatile("{\n.reg .pred p;\nsetp.ne.b32 p, %1, 0;\n@p red.relaxed.gpu.global.add.u32 [%0], 1;\n}" ::"l"(a), "r"((int)p) : "memory");
}
__device__ __forceinline__ bool mbar_try(uint32_t bar, uint32_t parity) {
  uint32_t ok;
  asm volatile("{\n.reg .pred p;\nmbarrier.test_wait.parity.shared::cta.b64 p, [%1], %2;\nselp.u32 %0, 1, 0, p;\n}" : "=r"(ok) : "r"(bar), "r"(parity) : "memory");
  return ok;
}
__device__ __forceinline__ void mbar_wait(uint32_t bar, uint32_t parity) {
  asm volatile(
      "{\n.reg .pred p;\n.reg .u32 n;\nmov.u32 n, 0;\n"
      "W_LOOP:\nmbarrier.try_wait.parity.shared::cta.b64 p, [%0], %1;\n@p bra W_DONE;\n"
      "add.u32 n, n, 1;\nsetp.lt.u32 p, n, 0x40000;\n@p bra W_LOOP;\ntrap;\nW_DONE:\n}" ::"r"(bar), "r"(parity) : "memory");
}
__device__ __forceinline__ void bulk_load(uint32_t dst, const void* src, uint32_t bytes, uint32_t bar) {
  asm volatile("cp.async.bulk.shared::cluster.global.mbarrier::complete_tx::bytes [%0], [%1], %2, [%3];" ::"r"(dst), "l"(src), "r"(bytes), "r"(bar) : "memory");
}
__device__ __forceinline__ void cp16(uint32_t dst, const void* src) { asm volatile("cp.async.cg.shared.global [%0], [%1], 16;" ::"r"(dst), "l"(src) : "memory"); }
__device__ __forceinline__ void spin_guard(uint32_t t0) { if ((uint32_t)clock() - t0 > (1u << 30)) __trap(); }
__device__ __forceinline__ float tagf(float v, uint32_t tag) { return __uint_as_float((__float_as_uint(v) & ~1u) | tag); }
__device__ __forceinline__ float untag(float v) { return __uint_as_float(__float_as_uint(v) & ~1u); }
__device__ __forceinline__ void st_x2(float2* p, float a, float b) { asm volatile("st.relaxed.gpu.global.v2.f32 [%0], {%1,%2};" ::"l"(p), "f"(a), "f"(b) : "memory"); }
__device__ __forceinline__ float2 ld_x2(const float2* p) { float2 v; asm volatile("ld.relaxed.gpu.global.v2.f32 {%0,%1}, [%2];" : "=f"(v.x), "=f"(v.y) : "l"(p) : "memory"); return v; }
__device__ __forceinline__ void st_u2(uint2* p, uint32_t a, uint32_t b) { asm volatile("st.relaxed.gpu.global.v2.u32 [%0], {%1,%2};" ::"l"(p), "r"(a), "r"(b) : "memory"); }
__device__ __forceinline__ void prefetch2d(const CUtensorMap* m, int c0, int c1) { asm volatile("cp.async.bulk.prefetch.tensor.2d.L2.global [%0, {%1, %2}];" ::"l"(m), "r"(c0), "r"(c1) : "memory"); }
__device__ __forceinline__ void prefetch1d(const void* p, uint32_t bytes) { asm volatile("cp.async.bulk.prefetch.L2.global [%0], %1;" ::"l"(p), "r"(bytes) : "memory"); }
__device__ __forceinline__ uint32_t ld_x1(const void* p) { uint32_t v; asm volatile("ld.relaxed.gpu.global.u32 %0, [%1];" : "=r"(v) : "l"(p) : "memory"); return v; }
__device__ __forceinline__ uint4 ld_x4(const void* p) { uint4 v; asm volatile("ld.relaxed.gpu.global.v4.u32 {%0,%1,%2,%3}, [%4];" : "=r"(v.x), "=r"(v.y), "=r"(v.z), "=r"(v.w) : "l"(p) : "memory"); return v; }
__device__ __forceinline__ void st_x4(void* p, uint32_t a, uint32_t b, uint32_t c, uint32_t d) { asm volatile("st.relaxed.gpu.global.v4.u32 [%0], {%1,%2,%3,%4};" ::"l"(p), "r"(a), "r"(b), "r"(c), "r"(d) : "memory"); }
__device__ __forceinline__ uint32_t mapa(uint32_t a, uint32_t cta) { uint32_t r; asm volatile("mapa.shared::cluster.u32 %0, %1, %2;" : "=r"(r) : "r"(a), "r"(cta)); return r; }
__device__ __forceinline__ void stsm4t(uint32_t a, uint32_t r0, uint32_t r1, uint32_t r2, uint32_t r3) {
  asm volatile("stmatrix.sync.aligned.m8n8.x4.trans.shared.b16 [%0], {%1,%2,%3,%4};" ::"r"(a), "r"(r0), "r"(r1), "r"(r2), "r"(r3) : "memory");
}
__device__ __forceinline__ void hint_add(unsigned* p) { asm volatile("red.relaxed.gpu.global.add.u32 [%0], 1;" ::"l"(p) : "memory"); }
__device__ __forceinline__ void hint_wait(const unsigned* p, unsigned target) {
  const uint32_t t0 = (uint32_t)clock();
  while ((int)(ld_x1(p) - target) < 0) spin_guard(t0);
}
__device__ __forceinline__ void bulk_done_signal(unsigned* p) {
  asm volatile("cp.async.bulk.commit_group;\ncp.async.bulk.wait_group 0;\nfence.proxy.async.global;" ::: "memory");
  hint_add(p);
}
__device__ __forceinline__ void flag_wait(const unsigned* p, unsigned target) {
  hint_wait(p, target);
  asm volatile("fence.proxy.async.global;" ::: "memory");
}
__device__ __forceinline__ void tma2d(uint32_t dst, const CUtensorMap* m, uint32_t bar, int c0, int c1) {
  asm volatile("cp.async.bulk.tensor.2d.shared::cluster.global.mbarrier::complete_tx::bytes [%0], [%1, {%3, %4}], [%2];" ::"r"(dst), "l"(m), "r"(bar), "r"(c0), "r"(c1) : "memory");
}
__device__ __forceinline__ void tma3d(uint32_t dst, const CUtensorMap* m, uint32_t bar, int c0, int c1, int c2) {
  asm volatile("cp.async.bulk.tensor.3d.shared::cluster.global.mbarrier::complete_tx::bytes [%0], [%1, {%3, %4, %5}], [%2];" ::"r"(dst), "l"(m), "r"(bar), "r"(c0), "r"(c1), "r"(c2) : "memory");
}
__device__ __forceinline__ void tma4d(uint32_t dst, const CUtensorMap* m, uint32_t bar, int c0, int c1, int c2, int c3) {
  asm volatile("cp.async.bulk.tensor.4d.shared::cluster.global.mbarrier::complete_tx::bytes [%0], [%1, {%3, %4, %5, %6}], [%2];" ::"r"(dst), "l"(m), "r"(bar), "r"(c0), "r"(c1), "r"(c2), "r"(c3) : "memory");
}
__device__ __forceinline__ void wg_fence() { asm volatile("wgmma.fence.sync.aligned;" ::: "memory"); }
__device__ __forceinline__ void wg_commit() { asm volatile("wgmma.commit_group.sync.aligned;" ::: "memory"); }
template <int N> __device__ __forceinline__ void wg_wait() { asm volatile("wgmma.wait_group.sync.aligned %0;" ::"n"(N) : "memory"); }
template <int O, int N, int NN> __device__ __forceinline__ void fence_regs(float (&d)[NN]) {
#pragma unroll
  for (int i = 0; i < N; i++) asm volatile("" : "+f"(d[O + i])::"memory");
}
__device__ __forceinline__ uint32_t pack_bf16(float lo, float hi) {
  uint32_t r; asm("cvt.rn.bf16x2.f32 %0, %1, %2;" : "=r"(r) : "f"(hi), "f"(lo)); return r;
}
__device__ __forceinline__ uint32_t pack_pin(float lo, float hi) {
  uint32_t r; asm volatile("cvt.rn.bf16x2.f32 %0, %1, %2;" : "=r"(r) : "f"(hi), "f"(lo) : "memory"); return r;
}
__device__ __forceinline__ float bf_lo(uint32_t u) { return __uint_as_float(u << 16); }
__device__ __forceinline__ float bf_hi(uint32_t u) { return __uint_as_float(u & 0xffff0000u); }

__device__ __forceinline__ uint64_t d128(uint32_t lo) { uint64_t d; asm("mov.b64 %0, {%1, 0x40000040};" : "=l"(d) : "r"(lo)); return d; }
__device__ __forceinline__ uint64_t d64(uint32_t lo) { uint64_t d; asm("mov.b64 %0, {%1, 0x80000020};" : "=l"(d) : "r"(lo)); return d; }
template<int O,int TB,int ACC,int NN> __device__ __forceinline__ void mma_ss64(float (&d)[NN], uint64_t da, uint64_t db, int sd = 0){
  if constexpr (ACC == 1) asm volatile("wgmma.mma_async.sync.aligned.m64n64k16.f32.bf16.bf16 {%0,%1,%2,%3,%4,%5,%6,%7,%8,%9,%10,%11,%12,%13,%14,%15,%16,%17,%18,%19,%20,%21,%22,%23,%24,%25,%26,%27,%28,%29,%30,%31}, %32, %33, 1, 1, 1, %35, %34;"
   : "+f"(d[O+0]), "+f"(d[O+1]), "+f"(d[O+2]), "+f"(d[O+3]), "+f"(d[O+4]), "+f"(d[O+5]), "+f"(d[O+6]), "+f"(d[O+7]), "+f"(d[O+8]), "+f"(d[O+9]), "+f"(d[O+10]), "+f"(d[O+11]), "+f"(d[O+12]), "+f"(d[O+13]), "+f"(d[O+14]), "+f"(d[O+15]), "+f"(d[O+16]), "+f"(d[O+17]), "+f"(d[O+18]), "+f"(d[O+19]), "+f"(d[O+20]), "+f"(d[O+21]), "+f"(d[O+22]), "+f"(d[O+23]), "+f"(d[O+24]), "+f"(d[O+25]), "+f"(d[O+26]), "+f"(d[O+27]), "+f"(d[O+28]), "+f"(d[O+29]), "+f"(d[O+30]), "+f"(d[O+31])
   : "l"(da), "l"(db), "n"(TB & 1), "n"(TB >> 1));
  else if constexpr (ACC == 0) asm volatile("wgmma.mma_async.sync.aligned.m64n64k16.f32.bf16.bf16 {%0,%1,%2,%3,%4,%5,%6,%7,%8,%9,%10,%11,%12,%13,%14,%15,%16,%17,%18,%19,%20,%21,%22,%23,%24,%25,%26,%27,%28,%29,%30,%31}, %32, %33, 0, 1, 1, %35, %34;"
   : "=f"(d[O+0]), "=f"(d[O+1]), "=f"(d[O+2]), "=f"(d[O+3]), "=f"(d[O+4]), "=f"(d[O+5]), "=f"(d[O+6]), "=f"(d[O+7]), "=f"(d[O+8]), "=f"(d[O+9]), "=f"(d[O+10]), "=f"(d[O+11]), "=f"(d[O+12]), "=f"(d[O+13]), "=f"(d[O+14]), "=f"(d[O+15]), "=f"(d[O+16]), "=f"(d[O+17]), "=f"(d[O+18]), "=f"(d[O+19]), "=f"(d[O+20]), "=f"(d[O+21]), "=f"(d[O+22]), "=f"(d[O+23]), "=f"(d[O+24]), "=f"(d[O+25]), "=f"(d[O+26]), "=f"(d[O+27]), "=f"(d[O+28]), "=f"(d[O+29]), "=f"(d[O+30]), "=f"(d[O+31])
   : "l"(da), "l"(db), "n"(TB & 1), "n"(TB >> 1));
  else asm volatile("{\n.reg .pred p;\nsetp.ne.b32 p, %36, 0;\nwgmma.mma_async.sync.aligned.m64n64k16.f32.bf16.bf16 {%0,%1,%2,%3,%4,%5,%6,%7,%8,%9,%10,%11,%12,%13,%14,%15,%16,%17,%18,%19,%20,%21,%22,%23,%24,%25,%26,%27,%28,%29,%30,%31}, %32, %33, p, 1, 1, %35, %34;\n}"
   : "+f"(d[O+0]), "+f"(d[O+1]), "+f"(d[O+2]), "+f"(d[O+3]), "+f"(d[O+4]), "+f"(d[O+5]), "+f"(d[O+6]), "+f"(d[O+7]), "+f"(d[O+8]), "+f"(d[O+9]), "+f"(d[O+10]), "+f"(d[O+11]), "+f"(d[O+12]), "+f"(d[O+13]), "+f"(d[O+14]), "+f"(d[O+15]), "+f"(d[O+16]), "+f"(d[O+17]), "+f"(d[O+18]), "+f"(d[O+19]), "+f"(d[O+20]), "+f"(d[O+21]), "+f"(d[O+22]), "+f"(d[O+23]), "+f"(d[O+24]), "+f"(d[O+25]), "+f"(d[O+26]), "+f"(d[O+27]), "+f"(d[O+28]), "+f"(d[O+29]), "+f"(d[O+30]), "+f"(d[O+31])
   : "l"(da), "l"(db), "n"(TB & 1), "n"(TB >> 1), "r"(sd));
}
template<int O,int TB,int ACC,int NN> __device__ __forceinline__ void mma_rs64(float (&d)[NN], uint32_t a0, uint32_t a1, uint32_t a2, uint32_t a3, uint64_t db, int sd = 0){
  if constexpr (ACC == 1) asm volatile("wgmma.mma_async.sync.aligned.m64n64k16.f32.bf16.bf16 {%0,%1,%2,%3,%4,%5,%6,%7,%8,%9,%10,%11,%12,%13,%14,%15,%16,%17,%18,%19,%20,%21,%22,%23,%24,%25,%26,%27,%28,%29,%30,%31}, {%32,%33,%34,%35}, %36, 1, 1, 1, %37;"
   : "+f"(d[O+0]), "+f"(d[O+1]), "+f"(d[O+2]), "+f"(d[O+3]), "+f"(d[O+4]), "+f"(d[O+5]), "+f"(d[O+6]), "+f"(d[O+7]), "+f"(d[O+8]), "+f"(d[O+9]), "+f"(d[O+10]), "+f"(d[O+11]), "+f"(d[O+12]), "+f"(d[O+13]), "+f"(d[O+14]), "+f"(d[O+15]), "+f"(d[O+16]), "+f"(d[O+17]), "+f"(d[O+18]), "+f"(d[O+19]), "+f"(d[O+20]), "+f"(d[O+21]), "+f"(d[O+22]), "+f"(d[O+23]), "+f"(d[O+24]), "+f"(d[O+25]), "+f"(d[O+26]), "+f"(d[O+27]), "+f"(d[O+28]), "+f"(d[O+29]), "+f"(d[O+30]), "+f"(d[O+31])
   : "r"(a0), "r"(a1), "r"(a2), "r"(a3), "l"(db), "n"(TB));
  else if constexpr (ACC == 0) asm volatile("wgmma.mma_async.sync.aligned.m64n64k16.f32.bf16.bf16 {%0,%1,%2,%3,%4,%5,%6,%7,%8,%9,%10,%11,%12,%13,%14,%15,%16,%17,%18,%19,%20,%21,%22,%23,%24,%25,%26,%27,%28,%29,%30,%31}, {%32,%33,%34,%35}, %36, 0, 1, 1, %37;"
   : "=f"(d[O+0]), "=f"(d[O+1]), "=f"(d[O+2]), "=f"(d[O+3]), "=f"(d[O+4]), "=f"(d[O+5]), "=f"(d[O+6]), "=f"(d[O+7]), "=f"(d[O+8]), "=f"(d[O+9]), "=f"(d[O+10]), "=f"(d[O+11]), "=f"(d[O+12]), "=f"(d[O+13]), "=f"(d[O+14]), "=f"(d[O+15]), "=f"(d[O+16]), "=f"(d[O+17]), "=f"(d[O+18]), "=f"(d[O+19]), "=f"(d[O+20]), "=f"(d[O+21]), "=f"(d[O+22]), "=f"(d[O+23]), "=f"(d[O+24]), "=f"(d[O+25]), "=f"(d[O+26]), "=f"(d[O+27]), "=f"(d[O+28]), "=f"(d[O+29]), "=f"(d[O+30]), "=f"(d[O+31])
   : "r"(a0), "r"(a1), "r"(a2), "r"(a3), "l"(db), "n"(TB));
  else asm volatile("{\n.reg .pred p;\nsetp.ne.b32 p, %38, 0;\nwgmma.mma_async.sync.aligned.m64n64k16.f32.bf16.bf16 {%0,%1,%2,%3,%4,%5,%6,%7,%8,%9,%10,%11,%12,%13,%14,%15,%16,%17,%18,%19,%20,%21,%22,%23,%24,%25,%26,%27,%28,%29,%30,%31}, {%32,%33,%34,%35}, %36, p, 1, 1, %37;\n}"
   : "+f"(d[O+0]), "+f"(d[O+1]), "+f"(d[O+2]), "+f"(d[O+3]), "+f"(d[O+4]), "+f"(d[O+5]), "+f"(d[O+6]), "+f"(d[O+7]), "+f"(d[O+8]), "+f"(d[O+9]), "+f"(d[O+10]), "+f"(d[O+11]), "+f"(d[O+12]), "+f"(d[O+13]), "+f"(d[O+14]), "+f"(d[O+15]), "+f"(d[O+16]), "+f"(d[O+17]), "+f"(d[O+18]), "+f"(d[O+19]), "+f"(d[O+20]), "+f"(d[O+21]), "+f"(d[O+22]), "+f"(d[O+23]), "+f"(d[O+24]), "+f"(d[O+25]), "+f"(d[O+26]), "+f"(d[O+27]), "+f"(d[O+28]), "+f"(d[O+29]), "+f"(d[O+30]), "+f"(d[O+31])
   : "r"(a0), "r"(a1), "r"(a2), "r"(a3), "l"(db), "n"(TB), "r"(sd));
}
template<int O,int TB,int ACC,int NN> __device__ __forceinline__ void mma_ss128(float (&d)[NN], uint64_t da, uint64_t db, int sd = 0){
  if constexpr (ACC == 1) asm volatile("wgmma.mma_async.sync.aligned.m64n128k16.f32.bf16.bf16 {%0,%1,%2,%3,%4,%5,%6,%7,%8,%9,%10,%11,%12,%13,%14,%15,%16,%17,%18,%19,%20,%21,%22,%23,%24,%25,%26,%27,%28,%29,%30,%31,%32,%33,%34,%35,%36,%37,%38,%39,%40,%41,%42,%43,%44,%45,%46,%47,%48,%49,%50,%51,%52,%53,%54,%55,%56,%57,%58,%59,%60,%61,%62,%63}, %64, %65, 1, 1, 1, %67, %66;"
   : "+f"(d[O+0]), "+f"(d[O+1]), "+f"(d[O+2]), "+f"(d[O+3]), "+f"(d[O+4]), "+f"(d[O+5]), "+f"(d[O+6]), "+f"(d[O+7]), "+f"(d[O+8]), "+f"(d[O+9]), "+f"(d[O+10]), "+f"(d[O+11]), "+f"(d[O+12]), "+f"(d[O+13]), "+f"(d[O+14]), "+f"(d[O+15]), "+f"(d[O+16]), "+f"(d[O+17]), "+f"(d[O+18]), "+f"(d[O+19]), "+f"(d[O+20]), "+f"(d[O+21]), "+f"(d[O+22]), "+f"(d[O+23]), "+f"(d[O+24]), "+f"(d[O+25]), "+f"(d[O+26]), "+f"(d[O+27]), "+f"(d[O+28]), "+f"(d[O+29]), "+f"(d[O+30]), "+f"(d[O+31]), "+f"(d[O+32]), "+f"(d[O+33]), "+f"(d[O+34]), "+f"(d[O+35]), "+f"(d[O+36]), "+f"(d[O+37]), "+f"(d[O+38]), "+f"(d[O+39]), "+f"(d[O+40]), "+f"(d[O+41]), "+f"(d[O+42]), "+f"(d[O+43]), "+f"(d[O+44]), "+f"(d[O+45]), "+f"(d[O+46]), "+f"(d[O+47]), "+f"(d[O+48]), "+f"(d[O+49]), "+f"(d[O+50]), "+f"(d[O+51]), "+f"(d[O+52]), "+f"(d[O+53]), "+f"(d[O+54]), "+f"(d[O+55]), "+f"(d[O+56]), "+f"(d[O+57]), "+f"(d[O+58]), "+f"(d[O+59]), "+f"(d[O+60]), "+f"(d[O+61]), "+f"(d[O+62]), "+f"(d[O+63])
   : "l"(da), "l"(db), "n"(TB & 1), "n"(TB >> 1));
  else if constexpr (ACC == 0) asm volatile("wgmma.mma_async.sync.aligned.m64n128k16.f32.bf16.bf16 {%0,%1,%2,%3,%4,%5,%6,%7,%8,%9,%10,%11,%12,%13,%14,%15,%16,%17,%18,%19,%20,%21,%22,%23,%24,%25,%26,%27,%28,%29,%30,%31,%32,%33,%34,%35,%36,%37,%38,%39,%40,%41,%42,%43,%44,%45,%46,%47,%48,%49,%50,%51,%52,%53,%54,%55,%56,%57,%58,%59,%60,%61,%62,%63}, %64, %65, 0, 1, 1, %67, %66;"
   : "=f"(d[O+0]), "=f"(d[O+1]), "=f"(d[O+2]), "=f"(d[O+3]), "=f"(d[O+4]), "=f"(d[O+5]), "=f"(d[O+6]), "=f"(d[O+7]), "=f"(d[O+8]), "=f"(d[O+9]), "=f"(d[O+10]), "=f"(d[O+11]), "=f"(d[O+12]), "=f"(d[O+13]), "=f"(d[O+14]), "=f"(d[O+15]), "=f"(d[O+16]), "=f"(d[O+17]), "=f"(d[O+18]), "=f"(d[O+19]), "=f"(d[O+20]), "=f"(d[O+21]), "=f"(d[O+22]), "=f"(d[O+23]), "=f"(d[O+24]), "=f"(d[O+25]), "=f"(d[O+26]), "=f"(d[O+27]), "=f"(d[O+28]), "=f"(d[O+29]), "=f"(d[O+30]), "=f"(d[O+31]), "=f"(d[O+32]), "=f"(d[O+33]), "=f"(d[O+34]), "=f"(d[O+35]), "=f"(d[O+36]), "=f"(d[O+37]), "=f"(d[O+38]), "=f"(d[O+39]), "=f"(d[O+40]), "=f"(d[O+41]), "=f"(d[O+42]), "=f"(d[O+43]), "=f"(d[O+44]), "=f"(d[O+45]), "=f"(d[O+46]), "=f"(d[O+47]), "=f"(d[O+48]), "=f"(d[O+49]), "=f"(d[O+50]), "=f"(d[O+51]), "=f"(d[O+52]), "=f"(d[O+53]), "=f"(d[O+54]), "=f"(d[O+55]), "=f"(d[O+56]), "=f"(d[O+57]), "=f"(d[O+58]), "=f"(d[O+59]), "=f"(d[O+60]), "=f"(d[O+61]), "=f"(d[O+62]), "=f"(d[O+63])
   : "l"(da), "l"(db), "n"(TB & 1), "n"(TB >> 1));
  else asm volatile("{\n.reg .pred p;\nsetp.ne.b32 p, %68, 0;\nwgmma.mma_async.sync.aligned.m64n128k16.f32.bf16.bf16 {%0,%1,%2,%3,%4,%5,%6,%7,%8,%9,%10,%11,%12,%13,%14,%15,%16,%17,%18,%19,%20,%21,%22,%23,%24,%25,%26,%27,%28,%29,%30,%31,%32,%33,%34,%35,%36,%37,%38,%39,%40,%41,%42,%43,%44,%45,%46,%47,%48,%49,%50,%51,%52,%53,%54,%55,%56,%57,%58,%59,%60,%61,%62,%63}, %64, %65, p, 1, 1, %67, %66;\n}"
   : "+f"(d[O+0]), "+f"(d[O+1]), "+f"(d[O+2]), "+f"(d[O+3]), "+f"(d[O+4]), "+f"(d[O+5]), "+f"(d[O+6]), "+f"(d[O+7]), "+f"(d[O+8]), "+f"(d[O+9]), "+f"(d[O+10]), "+f"(d[O+11]), "+f"(d[O+12]), "+f"(d[O+13]), "+f"(d[O+14]), "+f"(d[O+15]), "+f"(d[O+16]), "+f"(d[O+17]), "+f"(d[O+18]), "+f"(d[O+19]), "+f"(d[O+20]), "+f"(d[O+21]), "+f"(d[O+22]), "+f"(d[O+23]), "+f"(d[O+24]), "+f"(d[O+25]), "+f"(d[O+26]), "+f"(d[O+27]), "+f"(d[O+28]), "+f"(d[O+29]), "+f"(d[O+30]), "+f"(d[O+31]), "+f"(d[O+32]), "+f"(d[O+33]), "+f"(d[O+34]), "+f"(d[O+35]), "+f"(d[O+36]), "+f"(d[O+37]), "+f"(d[O+38]), "+f"(d[O+39]), "+f"(d[O+40]), "+f"(d[O+41]), "+f"(d[O+42]), "+f"(d[O+43]), "+f"(d[O+44]), "+f"(d[O+45]), "+f"(d[O+46]), "+f"(d[O+47]), "+f"(d[O+48]), "+f"(d[O+49]), "+f"(d[O+50]), "+f"(d[O+51]), "+f"(d[O+52]), "+f"(d[O+53]), "+f"(d[O+54]), "+f"(d[O+55]), "+f"(d[O+56]), "+f"(d[O+57]), "+f"(d[O+58]), "+f"(d[O+59]), "+f"(d[O+60]), "+f"(d[O+61]), "+f"(d[O+62]), "+f"(d[O+63])
   : "l"(da), "l"(db), "n"(TB & 1), "n"(TB >> 1), "r"(sd));
}
template<int O,int TB,int ACC,int NN> __device__ __forceinline__ void mma_rs128(float (&d)[NN], uint32_t a0, uint32_t a1, uint32_t a2, uint32_t a3, uint64_t db, int sd = 0){
  if constexpr (ACC == 1) asm volatile("wgmma.mma_async.sync.aligned.m64n128k16.f32.bf16.bf16 {%0,%1,%2,%3,%4,%5,%6,%7,%8,%9,%10,%11,%12,%13,%14,%15,%16,%17,%18,%19,%20,%21,%22,%23,%24,%25,%26,%27,%28,%29,%30,%31,%32,%33,%34,%35,%36,%37,%38,%39,%40,%41,%42,%43,%44,%45,%46,%47,%48,%49,%50,%51,%52,%53,%54,%55,%56,%57,%58,%59,%60,%61,%62,%63}, {%64,%65,%66,%67}, %68, 1, 1, 1, %69;"
   : "+f"(d[O+0]), "+f"(d[O+1]), "+f"(d[O+2]), "+f"(d[O+3]), "+f"(d[O+4]), "+f"(d[O+5]), "+f"(d[O+6]), "+f"(d[O+7]), "+f"(d[O+8]), "+f"(d[O+9]), "+f"(d[O+10]), "+f"(d[O+11]), "+f"(d[O+12]), "+f"(d[O+13]), "+f"(d[O+14]), "+f"(d[O+15]), "+f"(d[O+16]), "+f"(d[O+17]), "+f"(d[O+18]), "+f"(d[O+19]), "+f"(d[O+20]), "+f"(d[O+21]), "+f"(d[O+22]), "+f"(d[O+23]), "+f"(d[O+24]), "+f"(d[O+25]), "+f"(d[O+26]), "+f"(d[O+27]), "+f"(d[O+28]), "+f"(d[O+29]), "+f"(d[O+30]), "+f"(d[O+31]), "+f"(d[O+32]), "+f"(d[O+33]), "+f"(d[O+34]), "+f"(d[O+35]), "+f"(d[O+36]), "+f"(d[O+37]), "+f"(d[O+38]), "+f"(d[O+39]), "+f"(d[O+40]), "+f"(d[O+41]), "+f"(d[O+42]), "+f"(d[O+43]), "+f"(d[O+44]), "+f"(d[O+45]), "+f"(d[O+46]), "+f"(d[O+47]), "+f"(d[O+48]), "+f"(d[O+49]), "+f"(d[O+50]), "+f"(d[O+51]), "+f"(d[O+52]), "+f"(d[O+53]), "+f"(d[O+54]), "+f"(d[O+55]), "+f"(d[O+56]), "+f"(d[O+57]), "+f"(d[O+58]), "+f"(d[O+59]), "+f"(d[O+60]), "+f"(d[O+61]), "+f"(d[O+62]), "+f"(d[O+63])
   : "r"(a0), "r"(a1), "r"(a2), "r"(a3), "l"(db), "n"(TB));
  else if constexpr (ACC == 0) asm volatile("wgmma.mma_async.sync.aligned.m64n128k16.f32.bf16.bf16 {%0,%1,%2,%3,%4,%5,%6,%7,%8,%9,%10,%11,%12,%13,%14,%15,%16,%17,%18,%19,%20,%21,%22,%23,%24,%25,%26,%27,%28,%29,%30,%31,%32,%33,%34,%35,%36,%37,%38,%39,%40,%41,%42,%43,%44,%45,%46,%47,%48,%49,%50,%51,%52,%53,%54,%55,%56,%57,%58,%59,%60,%61,%62,%63}, {%64,%65,%66,%67}, %68, 0, 1, 1, %69;"
   : "=f"(d[O+0]), "=f"(d[O+1]), "=f"(d[O+2]), "=f"(d[O+3]), "=f"(d[O+4]), "=f"(d[O+5]), "=f"(d[O+6]), "=f"(d[O+7]), "=f"(d[O+8]), "=f"(d[O+9]), "=f"(d[O+10]), "=f"(d[O+11]), "=f"(d[O+12]), "=f"(d[O+13]), "=f"(d[O+14]), "=f"(d[O+15]), "=f"(d[O+16]), "=f"(d[O+17]), "=f"(d[O+18]), "=f"(d[O+19]), "=f"(d[O+20]), "=f"(d[O+21]), "=f"(d[O+22]), "=f"(d[O+23]), "=f"(d[O+24]), "=f"(d[O+25]), "=f"(d[O+26]), "=f"(d[O+27]), "=f"(d[O+28]), "=f"(d[O+29]), "=f"(d[O+30]), "=f"(d[O+31]), "=f"(d[O+32]), "=f"(d[O+33]), "=f"(d[O+34]), "=f"(d[O+35]), "=f"(d[O+36]), "=f"(d[O+37]), "=f"(d[O+38]), "=f"(d[O+39]), "=f"(d[O+40]), "=f"(d[O+41]), "=f"(d[O+42]), "=f"(d[O+43]), "=f"(d[O+44]), "=f"(d[O+45]), "=f"(d[O+46]), "=f"(d[O+47]), "=f"(d[O+48]), "=f"(d[O+49]), "=f"(d[O+50]), "=f"(d[O+51]), "=f"(d[O+52]), "=f"(d[O+53]), "=f"(d[O+54]), "=f"(d[O+55]), "=f"(d[O+56]), "=f"(d[O+57]), "=f"(d[O+58]), "=f"(d[O+59]), "=f"(d[O+60]), "=f"(d[O+61]), "=f"(d[O+62]), "=f"(d[O+63])
   : "r"(a0), "r"(a1), "r"(a2), "r"(a3), "l"(db), "n"(TB));
  else asm volatile("{\n.reg .pred p;\nsetp.ne.b32 p, %70, 0;\nwgmma.mma_async.sync.aligned.m64n128k16.f32.bf16.bf16 {%0,%1,%2,%3,%4,%5,%6,%7,%8,%9,%10,%11,%12,%13,%14,%15,%16,%17,%18,%19,%20,%21,%22,%23,%24,%25,%26,%27,%28,%29,%30,%31,%32,%33,%34,%35,%36,%37,%38,%39,%40,%41,%42,%43,%44,%45,%46,%47,%48,%49,%50,%51,%52,%53,%54,%55,%56,%57,%58,%59,%60,%61,%62,%63}, {%64,%65,%66,%67}, %68, p, 1, 1, %69;\n}"
   : "+f"(d[O+0]), "+f"(d[O+1]), "+f"(d[O+2]), "+f"(d[O+3]), "+f"(d[O+4]), "+f"(d[O+5]), "+f"(d[O+6]), "+f"(d[O+7]), "+f"(d[O+8]), "+f"(d[O+9]), "+f"(d[O+10]), "+f"(d[O+11]), "+f"(d[O+12]), "+f"(d[O+13]), "+f"(d[O+14]), "+f"(d[O+15]), "+f"(d[O+16]), "+f"(d[O+17]), "+f"(d[O+18]), "+f"(d[O+19]), "+f"(d[O+20]), "+f"(d[O+21]), "+f"(d[O+22]), "+f"(d[O+23]), "+f"(d[O+24]), "+f"(d[O+25]), "+f"(d[O+26]), "+f"(d[O+27]), "+f"(d[O+28]), "+f"(d[O+29]), "+f"(d[O+30]), "+f"(d[O+31]), "+f"(d[O+32]), "+f"(d[O+33]), "+f"(d[O+34]), "+f"(d[O+35]), "+f"(d[O+36]), "+f"(d[O+37]), "+f"(d[O+38]), "+f"(d[O+39]), "+f"(d[O+40]), "+f"(d[O+41]), "+f"(d[O+42]), "+f"(d[O+43]), "+f"(d[O+44]), "+f"(d[O+45]), "+f"(d[O+46]), "+f"(d[O+47]), "+f"(d[O+48]), "+f"(d[O+49]), "+f"(d[O+50]), "+f"(d[O+51]), "+f"(d[O+52]), "+f"(d[O+53]), "+f"(d[O+54]), "+f"(d[O+55]), "+f"(d[O+56]), "+f"(d[O+57]), "+f"(d[O+58]), "+f"(d[O+59]), "+f"(d[O+60]), "+f"(d[O+61]), "+f"(d[O+62]), "+f"(d[O+63])
   : "r"(a0), "r"(a1), "r"(a2), "r"(a3), "l"(db), "n"(TB), "r"(sd));
}

#define NEARLY 0
#define XAHEAD 3
#define HEADN 6
#define WBATCH 1
#define WB 8
#define WSLEEP 20
#define XSPREAD 4
#define NOSEND 0
#define MSPLIT 3
#define PFALL 1
#define L2PF 1
#define STAG 0
#define EPF 2
#define XNB 2
#define FNB 0
#define GNB 0
#define TH 5
#define PF0 4
#define FSPLIT 1
#define MGLU 1
#define SPACE 40
#define WPF 1
#define WAFTER 7
#define WPACE 0
#define GATE_AT 4
#define TPACE 40
#define PFMODE 0
#define MAPMODE 1
template <int V> struct IC { static constexpr int value = V; };
struct Maps { CUtensorMap x, ft, g64, u64, e, wr, wi, xs, ts, t, g32, u32, d224, o; };

constexpr int NCTA = 130;
constexpr int U = 16384;
constexpr int TB = 36864;
constexpr int OFF_RING = 8 * U, OFF_Z = 12 * U, OFF_XB = 12 * U, OFF_T = 13 * U, OFF_D = OFF_T;
constexpr int OFF_BAR = 14 * U, OFF_SP = OFF_BAR + 512, OFF_G = OFF_SP + 1024 + 128;
constexpr int SMEM_BYTES = OFF_G + 512;
constexpr int B_FX = 0, B_FA = 8, B_FT = 12, B_Z = 16, B_W = 24, B_HX = 25, B_TL = 26, B_HP = 27, B_WR = 30, B_E0 = 34;
constexpr int B_EA = 35, B_ET = 39, B_PZ = 43, B_RDY = 45, B_FE = 46;
constexpr int B_T = 50, B_XS = 51, B_G = 53, B_RD0 = 54, NBAR = 55;
__host__ __device__ constexpr int rslot(int n) { return n & 3; }
__host__ __device__ constexpr int rpar(int n) { return (n >> 2) & 1; }

__global__ void __cluster_dims__(2, 1, 1) __launch_bounds__(512, 1)
fused_kernel(Work* __restrict__ ws, const uint16_t* __restrict__ dtab, const __nv_bfloat16* __restrict__ w_r, const __nv_bfloat16* __restrict__ w_i,
             const __nv_bfloat16* __restrict__ gate_w, const __nv_bfloat16* __restrict__ x, const uint16_t* __restrict__ ftab,
             const __nv_bfloat16* __restrict__ Wg, const __nv_bfloat16* __restrict__ Wu, const __grid_constant__ Maps maps) {
  extern __shared__ __align__(1024) uint8_t smem[];
  if (threadIdx.x < 32 && elect_one()) {
#pragma unroll
    for (int i = 0; i < PF0; i++) asm volatile("prefetch.tensormap [%0];" ::"l"((const char*)&maps + i * 128) : "memory");
  }
  const uint32_t sb = smem_u32(smem);
  const uint32_t bars = sb + OFF_BAR;
  const int tid = threadIdx.x, lane = tid & 31;
  const int warp = __shfl_sync(0xffffffffu, tid >> 5, 0);
  const bool helper = blockIdx.x >= 128;
  const int cl = (blockIdx.x >> 1) & 63, rank = blockIdx.x & 1;
  const int q4 = (cl & 1) | ((cl >> 2) & 2), rb = ((cl >> 1) & 3) | ((cl >> 4) << 2);
  const int j = 2 * q4 + rank;
  const int f_full = 448 * q4 + (rank ? 256 : 0);
  const int f_half = 448 * q4 + (rank ? 224 : 192);
  const int kg = 2 * j + (rb >> 3), tn = rb & 7;

  if (tid == 64) { PROF_EV(0); PROF_CK(40); }
  if (warp < 8) {
    if (!helper) {
      if (tid < 16 * XNB) {
        const int r = 16 * j + (tid & 15);
        asm volatile("prefetch.global.L2 [%0];" ::"l"(x + (size_t)(2 * rb + (r >> 6) + 32 * (r & 63)) * 512 + 64 * (tid >> 4)));
      } else if (tid >= 128 && tid < 128 + 4 * FNB) {
        asm volatile("prefetch.global.L2 [%0];" ::"l"(ftab + (64 * j + 4 * rb + (tid & 3)) * 512 + 64 * ((tid - 128) >> 2)));
      } else if (tid >= 192 && tid < 192 + 8 * GNB) {
        asm volatile("prefetch.global.L2 [%0];" ::"l"(((tid & 4) ? Wu : Wg) + (size_t)(64 * ((tid - 192) >> 3) + 4 * rb + (tid & 3)) * 1792 + f_full));
      }
    }
    asm volatile("barrier.cluster.arrive.relaxed.aligned;" ::: "memory");
    asm volatile("setmaxnreg.inc.sync.aligned.u32 192;");
    if (!helper) {
      const int wg = warp >> 2, w = warp & 3, g = lane >> 2;
      const bool elect = (tid & 127) == 0;
      float cX[32], cA[64], cB[64], cC[64], ci[64], ct[64];
      const int zero = blockIdx.x >> 16;
      uint32_t h[56], yf[16];
      const uint32_t d0 = (sb & 0x3FFFF) >> 4;
      const uint32_t dK = d0 | (1u << 16), dN = d0 | (512u << 16);
      const uint32_t dX = dK + wg * 512;
      constexpr uint32_t RING = OFF_RING >> 4;
      auto waitA = [&](int n) { mbar_wait(bars + 8 * (B_FA + rslot(n)), rpar(n)); };
      auto freeA = [&](int n) { mbar_arrive_if(elect, bars + 8 * (B_EA + rslot(n))); };
      auto nop = [] {};

      asm volatile("bar.sync 0, 384;" ::: "memory");
#pragma unroll 1
      for (int i = 0; i < 4; i++) {
        const uint64_t dx = d128(dX + i * 2048), df = d128(dK + (OFF_XB >> 4) + (i & 1) * 1024);
        mbar_wait(bars + 8 * (B_FX + 2 * i), 0);
        wg_fence();
        mma_ss64<0, 0, 2>(cX, df, dx, i);
        mma_ss64<0, 0, 1>(cX, df + 2, dx + 2);
        wg_commit(); wg_wait<1>();
        mbar_arrive_if(elect && i, bars + 8 * (B_EA + rslot(i - 1)));
        mma_ss64<0, 0, 1>(cX, df + 4, dx + 4);
        mma_ss64<0, 0, 1>(cX, df + 6, dx + 6);
        if (i == 0 && tid == 0) PROF_EV(1);
        mbar_wait(bars + 8 * (B_FX + 2 * i + 1), 0);
        wg_fence();
#pragma unroll
        for (int k = 0; k < 4; k++) mma_ss64<0, 0, 1>(cX, df + (512 + k * 2), dx + (1024 + k * 2));
        wg_commit();
        waitA(i);
        wg_fence();
        const uint64_t da = d128(dX + i * 1024), db = d128(dN + RING + i * 1024);
        mma_ss128<0, 1, 2>(cA, da, db, i);
        wg_commit(); wg_wait<1>();
        mbar_arrive_if(elect, bars + 8 * (B_FE + i));
#pragma unroll
        for (int k = 1; k < 4; k++) mma_ss128<0, 1, 1>(cA, da + k * 2, db + k * 128);
        wg_commit();
      }
      fence_regs<0, 32>(cX);
#pragma unroll
      for (int e = 0; e < 16; e++) yf[e] = pack_pin(cX[2 * e], cX[2 * e + 1]);
      if (tid == 0) { PROF_EV(2); PROF_CK(42); }
      {
        waitA(4); mbar_wait(bars + 8 * B_E0, 0);
        const uint64_t de = d128(dN + (wg ? RING : OFF_XB >> 4));
        wg_fence();
        mma_rs128<0, 1, 0>(cB, yf[0], yf[1], yf[2], yf[3], de);
        wg_commit();
        wg_wait<1>();
        freeA(3);
#pragma unroll
        for (int k = 1; k < 4; k++) mma_rs128<0, 1, 1>(cB, yf[4 * k], yf[4 * k + 1], yf[4 * k + 2], yf[4 * k + 3], de + k * 128);
        wg_commit();
      }
      bool rel = false;
      auto acquire = [&](int n) {
        rel = elect;
        if (!mbar_try(bars + 8 * (B_FA + rslot(n)), rpar(n))) { wg_wait<0>(); freeA(n - 1); rel = false; waitA(n); }
      };
      auto freeP = [&](int n) { mbar_arrive_if(rel, bars + 8 * (B_EA + rslot(n - 1))); };
      auto ffn_step = [&](auto first, auto split, float (&acc)[64], int n, int kb, auto done, auto work) {
        constexpr int SPLIT = decltype(split)::value;
        acquire(n);
        wg_fence();
        const uint64_t dx = d128(dX + kb * 1024), db = d128(dN + RING + rslot(n) * 1024);
        mma_ss128<0, 1, decltype(first)::value>(acc, dx, db, kb);
#pragma unroll
        for (int k = 1; k < SPLIT; k++) mma_ss128<0, 1, 1>(acc, dx + k * 2, db + k * 128);
        wg_commit();
        work();
        wg_wait<1>();
        freeP(n);
        done();
        if (SPLIT < 4) {
          wg_fence();
#pragma unroll
          for (int k = SPLIT; k < 4; k++) mma_ss128<0, 1, 1>(acc, dx + k * 2, db + k * 128);
          wg_commit();
        }
      };
      {
        const int s0 = 2 * rb + wg, kr = 2 * ((s0 & 1) | ((s0 & 4) >> 1));
        const int m = lane >> 3, r = lane & 7;
        const uint32_t a0 = sb + OFF_XB + wg * 8192 + (((w >> 1) * 8 + (m >> 1)) * 2 + (w & 1)) * 256 + (m & 1) * 128 + ((r ^ (kr + (m & 1))) << 4);
        ffn_step(IC<1>(), IC<4>(), cA, 5, 4, [&] { fence_regs<0, 64>(cB); }, nop);
        asm volatile("bar.sync 5, 256;" ::: "memory");
        auto stage = [&](int i) {
          stsm4t(a0 + i * 1024, pack_bf16(cB[8 * i] - cB[34 + 8 * i], cB[8 * i + 1] - cB[35 + 8 * i]),
                 pack_bf16(cB[32 + 8 * i] + cB[8 * i + 2], cB[33 + 8 * i] + cB[8 * i + 3]),
                 pack_bf16(cB[8 * i + 4] - cB[38 + 8 * i], cB[8 * i + 5] - cB[39 + 8 * i]),
                 pack_bf16(cB[36 + 8 * i] + cB[8 * i + 6], cB[37 + 8 * i] + cB[8 * i + 7]));
          if (j == 0 && w == 0) {
            const uint32_t a1 = r ? sb + OFF_SP + 1024 : sb + OFF_SP + wg * 512 + (m & 1) * 256 + (m >> 1) * 128;
#pragma unroll
            for (int n = 2 * i; n < 2 * i + 2; n++)
              asm volatile("stmatrix.sync.aligned.m8n8.x4.shared.b16 [%0], {%1,%2,%3,%4};" ::"r"(a1 + ((n ^ (kr + (m >> 1)) ^ r) << 4)),
                           "r"(pack_bf16(cB[4 * n], cB[4 * n + 1])), "r"(pack_bf16(cB[4 * n + 2], cB[4 * n + 3])),
                           "r"(pack_bf16(cB[32 + 4 * n], cB[33 + 4 * n])), "r"(pack_bf16(cB[34 + 4 * n], cB[35 + 4 * n])) : "memory");
          }
        };
        auto publish = [&] {
          asm volatile("fence.proxy.async.shared::cta;" ::: "memory");
          __syncwarp();
          mbar_arrive_if(lane == 0, bars + 8 * (B_XS + wg));
          if (tid == 0) PROF_EV(3);
        };
        stage(0);
        ffn_step(IC<1>(), IC<FSPLIT>(), cA, 6, 5, nop, nop);
        stage(1);
        ffn_step(IC<1>(), IC<FSPLIT>(), cA, 7, 6, nop, nop);
        stage(2);
        ffn_step(IC<1>(), IC<2>(), cA, 8, 7, [&] { stage(3); }, nop);
        publish();
      }
      float g0 = 0.f, g1 = 0.f;
      uint32_t tag = 0;
      uint32_t ob[2] = {0, 0};
      auto glu = [&](auto& acc, int half, int ho, int i0, int i1) {
#pragma unroll
        for (int i = i0; i < i1; i++)
          asm volatile("{\n.reg .b32 a, b;\ncvt.rn.relu.bf16x2.f32 a, %2, %1;\ncvt.rn.bf16x2.f32 b, %4, %3;\nmul.rn.bf16x2 a, a, b;\nmul.rn.bf16x2 %0, a, %5;\n}"
                       : "=r"(h[ho + i]) : "f"(acc[2 * i]), "f"(acc[2 * i + 1]), "f"(acc[half + 2 * i]), "f"(acc[half + 1 + 2 * i]), "r"(ob[i & 1]) : "memory");
      };
      ffn_step(IC<2>(), IC<1>(), cB, 9, zero, nop, nop);
#pragma unroll 1
      for (int kb = 1; kb < 8; kb++)
        ffn_step(IC<1>(), IC<FSPLIT>(), cB, 9 + kb, kb, nop, [&] {
          if (kb == 4 + 2 * wg) {
            mbar_wait(bars + 8 * B_G, 0);
            const uint32_t gb0 = *(const uint32_t*)(smem + OFF_G + (wg * 64 + w * 16 + g) * 4), gb1 = *(const uint32_t*)(smem + OFF_G + (wg * 64 + w * 16 + g + 8) * 4);
            tag = gb0 & 1; g0 = __uint_as_float(gb0 & ~1u); g1 = __uint_as_float(gb1 & ~1u);
            ob[0] = pack_bf16(1.0f - g0, 1.0f - g0); ob[1] = pack_bf16(1.0f - g1, 1.0f - g1);
            glu(cA, 32, 0, 0, 16);
          }
        });
      if (tid == 0) { PROF_EV(4); PROF_CK(43); }
      auto m_step = [&](auto first, int i) {
        acquire(17 + i);
        wg_fence();
        const uint64_t dx = d128(dX + i * 2048), dm = d64(dN + RING + rslot(17 + i) * 1024);
        mma_ss64<0, 1, decltype(first)::value>(ct, dx, dm);
#pragma unroll
        for (int k = 1; k < MSPLIT; k++) mma_ss64<0, 1, 1>(ct, dx + ((k >> 2) * 1024 + (k & 3) * 2), dm + k * 64);
        wg_commit();
        wg_wait<1>();
        freeP(17 + i);
        wg_fence();
#pragma unroll
        for (int k = MSPLIT; k < 8; k++) mma_ss64<0, 1, 1>(ct, dx + ((k >> 2) * 1024 + (k & 3) * 2), dm + k * 64);
        wg_commit();
      };
      m_step(IC<0>(), 0);
#pragma unroll 1
      for (int i = 1; i < 5; i++) {
        if (i == 1 + 2 * wg) glu(cB, 32, 16, 0, 16);
        if (i < 4) m_step(IC<1>(), i);
      }
      if (tid == 0) { PROF_EV(5); PROF_CK(44); }
      ffn_step(IC<0>(), IC<1>(), cC, 21, 0, nop, nop);
#pragma unroll 1
      for (int kb = 1; kb < 8; kb++)
        ffn_step(IC<1>(), IC<FSPLIT>(), cC, 21 + kb, kb, [&] { mbar_arrive_if(elect && !(kb & 1), bars + 8 * (B_ET + (kb >> 1) - 1)); }, [&] {
          if (kb == 1 + wg) glu(ct, 16, 48, 0, 8);
        });

      auto twait = [&](uint32_t bar, uint32_t par, int) { mbar_wait(bar, par); };
      auto tr = [] {};
      const int fo = warp * 128 + lane;
      auto fetch = [&](uint4 (&pv)[4], int z) {
        twait(bars + 8 * (z < 4 ? B_Z + 2 * z + wg : B_HP + z - 4), 0, 8 + z);
        const uint8_t* src = smem + (z < 4 ? OFF_Z - z * U : z == 4 ? OFF_T : (z - 5) * U) + fo * 16;
#pragma unroll
        for (int i = 0; i < 4; i++) pv[i] = *(const uint4*)(src + i * 512);
      };
      auto check = [&](uint4 (&pv)[4], int z) {
        const uint32_t t0 = (uint32_t)clock();
        while (__any_sync(0xffffffffu, ((pv[0].x ^ tag) | (pv[1].x ^ tag) | (pv[2].x ^ tag) | (pv[3].x ^ tag)) & 1)) {
#pragma unroll
          for (int i = 0; i < 4; i++) pv[i] = ld_x4(ws->part + (size_t)((rb * 8 + j) * 3 + z - 4) * 1024 + fo + i * 32);
          spin_guard(t0);
        }
#pragma unroll
        for (int i = 0; i < 4; i++) pv[i].x &= ~1u;
      };
      const uint32_t peerZ = mapa(sb + OFF_Z + fo * 16, rank ^ 1), peerB = mapa(bars + 8 * (B_Z + wg), rank ^ 1);
      auto tile_mma = [&](auto off, int t, int k0, int k1, int init) {
        constexpr int O = decltype(off)::value;
        const uint64_t db = d128(dN + (t & 3) * (TB >> 4)), dw = db + rank * 256, dm = db + (rank ? 0 : 1536);
#pragma unroll
        for (int k = k0; k < k1; k++) {
          if (k == 0) mma_rs64<O, 1, 2>(ct, h[0], h[1], h[2], h[3], dw, init);
          else if (k < 14) mma_rs64<O, 1, 1>(ct, h[4 * k], h[4 * k + 1], h[4 * k + 2], h[4 * k + 3], k < 12 ? dw + k * 128 : dm + (k - 12) * 128);
          else mma_rs64<O, 1, 1>(ct, yf[4 * k - 56], yf[4 * k - 55], yf[4 * k - 54], yf[4 * k - 53], db + k * 128);
        }
      };
      auto tile = [&](auto off, int t) {
        constexpr int P = 32 - decltype(off)::value;
        const bool grid = t >= 4 && t < 7, pre = t != 1 && t != 5;
        const int zo = grid ? t - 4 : t == 7 ? 3 : t - 1, z = t - 2;
        const int owner = rb * 8 + 2 * ((q4 + zo + 1) & 3) + rank;
        uint4* dst = ws->part + (size_t)(owner * 3 + zo) * 1024 + fo;
        const uint32_t src = sb + (z < 4 ? OFF_Z - z * U : z == 4 ? OFF_T : (z - 5) * U) + fo * 16;
        twait(bars + 8 * (B_FT + (t & 3)), t >> 2, t);
        wg_fence();
        tile_mma(off, t, 0, TH, t >= 3 && t != 6);
        wg_commit();
        wg_wait<1>();
        mbar_arrive_if(elect && t < 6, bars + 8 * (B_ET + t - 1));
        if (t < 3) twait(bars + 8 * (t == 1 ? B_RD0 : B_RDY), 0, 14 + t);
        fence_regs<P, 32>(ct);
        uint32_t pk[16];
#pragma unroll
        for (int i = 0; i < 16; i++) pk[i] = pack_bf16(ct[P + 2 * i], ct[P + 2 * i + 1]);
        wg_fence();
#pragma unroll
        for (int i = 0; i < 4; i++) {
          asm volatile(
              "{\n.reg .pred p;\nsetp.ne.b32 p, %7, 0;\n@p st.relaxed.gpu.global.v4.u32 [%0], {%3,%4,%5,%6};\n"
              "@!p st.async.weak.shared::cluster.mbarrier::complete_tx::bytes.v4.b32 [%1], {%3,%4,%5,%6}, [%2];\n}" ::"l"(dst + i * 32),
              "r"(peerZ - zo * U + i * 512), "r"(peerB + 16 * zo), "r"((pk[4 * i] & ~(uint32_t)grid) | (tag & grid)), "r"(pk[4 * i + 1]), "r"(pk[4 * i + 2]),
              "r"(pk[4 * i + 3]), "r"((int)grid) : "memory");
          if (i == 3) hint_add_if(grid && lane == 0, &ws->cntP[32 * owner + zo]);
          tile_mma(off, t, TH + 2 * i, TH + 2 * i + 2, 0);
        }
        wg_commit();
        if (pre) twait(bars + 8 * (z < 4 ? B_Z + 2 * z + wg : B_HP + z - 4), 0, 8 + z);
        wg_fence();
        uint4 pv[4];
#pragma unroll
        for (int i = 0; i < 4; i++) {
          asm volatile("{\n.reg .pred p;\nsetp.ne.b32 p, %5, 0;\n@p ld.shared.v4.u32 {%0,%1,%2,%3}, [%4];\n}"
                       : "=r"(pv[i].x), "=r"(pv[i].y), "=r"(pv[i].z), "=r"(pv[i].w) : "r"(src + i * 512), "r"((int)pre) : "memory");
          tile_mma(off, t, TH + 8 + i, i < 3 ? TH + 9 + i : 18, 0);
        }
        wg_commit();
        if (pre) {
          if (z >= 4) check(pv, z);
#pragma unroll
          for (int i = 0; i < 4; i++) {
            const uint32_t a[4] = {pv[i].x, pv[i].y, pv[i].z, pv[i].w};
#pragma unroll
            for (int e = 0; e < 4; e++) { ct[P + 8 * i + 2 * e] = bf_lo(a[e]); ct[P + 8 * i + 2 * e + 1] = bf_hi(a[e]); }
          }
        }
      };
      asm volatile("barrier.cluster.wait.aligned;" ::: "memory");
      twait(bars + 8 * B_FT, 0, 0);
      wg_fence();
      tile_mma(IC<0>(), 0, 0, 5, zero);
      wg_commit();
      wg_wait<1>();
      mbar_arrive_if(elect, bars + 8 * (B_ET + 3));
      glu(cC, 32, 32, 0, 8);
      waitA(29 + wg);
      wg_fence();
      tile_mma(IC<0>(), 0, 5, 8, 0);
      tile_mma(IC<0>(), 0, 12, 14, 0);
      wg_commit();
      glu(cC, 32, 32, 8, 16);
      if (tid == 0) PROF_EV(6);
      if (tid == 128) PROF_EV(27);
      mbar_wait(bars + 8 * (j == 0 ? B_T : B_TL), 0);
      if (tid == 0) { PROF_EV(7); PROF_CK(45); }
      wg_fence();
      {
        const uint64_t dt = d128(dN + (OFF_T >> 4) + wg * 512), de = d128(dK + RING + (1 + wg) * 1024);
        mma_ss64<0, 1, 0>(ci, de, dt);
        mma_ss64<32, 1, 0>(ci, de + 512, dt);
#pragma unroll
        for (int k = 1; k < 4; k++) {
          mma_ss64<0, 1, 1>(ci, de + k * 2, dt + k * 128);
          mma_ss64<32, 1, 1>(ci, de + (512 + k * 2), dt + k * 128);
        }
        wg_commit();
      }
      tile_mma(IC<0>(), 0, 8, 12, 0);
      wg_commit();
      wg_wait<1>();
      if (elect) asm volatile("mbarrier.arrive.shared::cluster.b64 _, [%0];" ::"r"(mapa(bars + 8 * B_RDY, rank ^ 1)) : "memory");
      mbar_arrive_if(elect, bars + 8 * (B_PZ + 1));
      fence_regs<0, 64>(ci);
#pragma unroll
      for (int i = 0; i < 16; i++) {
        const float gg = ((i & 1) ? g1 : g0) * (2.0f / (2048.0f * 512.0f));
        if (i & 2) yf[i] = pack_pin((ci[2 * i] - ci[28 + 2 * i]) * gg, (ci[2 * i + 1] - ci[29 + 2 * i]) * gg);
        else yf[i] = pack_pin((ci[2 * i] + ci[36 + 2 * i]) * gg, (ci[2 * i + 1] + ci[37 + 2 * i]) * gg);
      }
      wg_fence();
      tile_mma(IC<0>(), 0, 14, 18, 0);
      wg_commit();
      if (tid == 0) PROF_EV(8);
      if (tid == 128) PROF_EV(28);
#pragma unroll 1
      for (int t = 1;; t += 2) {
        tile(IC<32>(), t);
        if (t == 7) break;
        tile(IC<0>(), t + 1);
      }
      if (tid == 0) { PROF_EV(9); PROF_CK(46); }
      if (tid == 128) PROF_EV(29);
      {
        float (&sum)[64] = ct;
        uint4 p2[4], p3[4];
        fetch(p3, 3);
        if (tid == 0) PROF_EV(25);
        fetch(p2, 6);
        if (tid == 0) PROF_EV(24);
        check(p2, 6);
#pragma unroll
        for (int i = 0; i < 4; i++) {
          const uint32_t b[4] = {p2[i].x, p2[i].y, p2[i].z, p2[i].w}, c[4] = {p3[i].x, p3[i].y, p3[i].z, p3[i].w};
#pragma unroll
          for (int e = 0; e < 4; e++) {
            sum[8 * i + 2 * e] += bf_lo(c[e]) + bf_lo(b[e]);
            sum[8 * i + 2 * e + 1] += bf_hi(c[e]) + bf_hi(b[e]);
          }
        }
        if (tid == 0) PROF_EV(14);
        wg_wait<0>();
        fence_regs<32, 32>(ct);
#pragma unroll
        for (int i = 0; i < 32; i++) sum[i] += ct[32 + i];
        const uint32_t stg = sb + OFF_T + warp * 2048;
        const int mr = (lane & 7) + ((lane >> 3) & 1) * 8, mc = lane >> 4;
#pragma unroll
        for (int i = 0; i < 4; i++) {
          const uint32_t a = stg + mr * 128 + (((2 * i + mc) ^ (mr & 7)) << 4);
          asm volatile("stmatrix.sync.aligned.m8n8.x4.shared.b16 [%0], {%1,%2,%3,%4};" ::"r"(a), "r"(pack_bf16(sum[8 * i], sum[8 * i + 1])),
                       "r"(pack_bf16(sum[8 * i + 2], sum[8 * i + 3])), "r"(pack_bf16(sum[8 * i + 4], sum[8 * i + 5])),
                       "r"(pack_bf16(sum[8 * i + 6], sum[8 * i + 7])) : "memory");
        }
        asm volatile("fence.proxy.async.shared::cta;" ::: "memory");
        __syncwarp();
        if (elect_one()) {
          asm volatile("cp.async.bulk.tensor.3d.global.shared::cta.bulk_group [%0, {%2, %3, %4}], [%1];" ::"l"(&maps.o), "r"(stg), "r"(64 * j),
                       "r"(16 * w), "r"(2 * rb + wg) : "memory");
          asm volatile("cp.async.bulk.commit_group;\ncp.async.bulk.wait_group.read 0;" ::: "memory");
        }
      }
      if (tid == 0) { PROF_EV(15); PROF_CK(41); }
      if (tid == 128) PROF_EV(30);
    }
  } else if (warp < 12) {
    asm volatile("setmaxnreg.dec.sync.aligned.u32 104;");
    asm volatile("barrier.cluster.arrive.relaxed.aligned;" ::: "memory");
    const int t = tid - 256, w = warp - 8;
    const uint32_t ep = ld_x1(&ws->epoch[blockIdx.x * 8]);
    const uint32_t tag = (ep + 1) & 1;
    auto w_issue = [&](const CUtensorMap* m) {

      if (elect_one()) { mbar_expect_tx(bars + 8 * (B_WR + w), 3072); tma4d(sb + OFF_T + w * 3072, m, bars + 8 * (B_WR + w), 16 * kg, 0, 2 * w, tn); }

          __syncwarp();
    };
    auto gate_rows = [&] {
      const int r = 16 * j + 4 * w + (lane >> 3);
      const uint4* pg = (const uint4*)gate_w + (lane & 7);
      {
        float a = 0.f;
        asm volatile("bar.sync 4, 256;" ::: "memory");
#pragma unroll 1
        for (int hf = 0; hf < 2; hf++) {
          uint4 v[4], u[4];
#pragma unroll
          for (int kb = 0; kb < 4; kb++) v[kb] = __ldg(pg + (4 * hf + kb) * 8);
          mbar_wait(bars + 8 * (B_FE + 1 + 2 * hf), 0);
          if (hf) w_issue(&maps.wr);
#pragma unroll
          for (int kb = 0; kb < 4; kb++) u[kb] = *(const uint4*)(smem + (4 * hf + kb) * U + r * 128 + (((lane ^ r) & 7) << 4));
#pragma unroll
          for (int kb = 0; kb < 4; kb++) {
            a = fmaf(bf_lo(u[kb].x), bf_lo(v[kb].x), a); a = fmaf(bf_hi(u[kb].x), bf_hi(v[kb].x), a);
            a = fmaf(bf_lo(u[kb].y), bf_lo(v[kb].y), a); a = fmaf(bf_hi(u[kb].y), bf_hi(v[kb].y), a);
            a = fmaf(bf_lo(u[kb].z), bf_lo(v[kb].z), a); a = fmaf(bf_hi(u[kb].z), bf_hi(v[kb].z), a);
            a = fmaf(bf_lo(u[kb].w), bf_lo(v[kb].w), a); a = fmaf(bf_hi(u[kb].w), bf_hi(v[kb].w), a);
          }
        }
#pragma unroll
        for (int o = 4; o; o >>= 1) a += __shfl_xor_sync(0xffffffffu, a, o);
        if ((lane & 7) == 0)
          asm volatile("st.relaxed.gpu.global.f32 [%0], %1;" ::"l"(ws->gate + rb * 128 + r), "f"(tagf(__fdividef(1.0f, 1.0f + __expf(-a)), tag)) : "memory");
        if (t == 0) PROF_EV(18);
      }
    };
    {
      const int g = lane >> 2, q = lane & 3;
      uint32_t wf[32];
      if (!helper) {
        gate_rows();
        const uint32_t wa = sb + OFF_T + w * (3072 + 4) + q * 48 + g * 2;
#pragma unroll 1
        for (int ri = 0; ri < 2; ri++) {
          mbar_wait(bars + 8 * (B_WR + w), ri);
#pragma unroll
          for (int n2 = 0; n2 < 32 / WB; n2++) {
            uint32_t v[WB];
#pragma unroll
            for (int i = 0; i < WB; i++) {
              const int e = n2 * WB + i;
              asm volatile("ld.shared.u16 %0, [%1];" : "=r"(v[i]) : "r"(wa + ((e >> 1) & 7) * 192 + (e & 1) * (1536 + 2) + (e >> 4) * 16) : "memory");
            }
#pragma unroll
            for (int i = 0; i < WB; i++) wf[n2 * WB + i] = __byte_perm(wf[n2 * WB + i], v[i], 0x5432);
            if (WSLEEP) { asm volatile("nanosleep.u32 %0;" ::"r"(WSLEEP + (v[WB - 1] >> 16)) : "memory"); }
          }
          __syncwarp();
          if (ri == 0) w_issue(&maps.wi);
        }
        asm volatile("bar.sync 1, 128;" ::: "memory");
        if (t == 0) PROF_EV(11);
      } else {
        asm volatile("bar.sync 4, 256;" ::: "memory");
        hint_wait(&ws->cntW[0], (ep + 1) * 128u);
        const uint32_t t0 = (uint32_t)clock();
#pragma unroll 1
        for (;;) {
          uint32_t bad = 0;
#pragma unroll
          for (int i = 0; i < 32; i++) {
            const float2 v = ld_x2((const float2*)ws->Wh + (i >> 4) * 2048 + 16 * w + g + 8 * (i & 1) + 64 * q + ((i >> 1) & 7) * 256);
            wf[i] = __float_as_uint(v.x); bad |= __float_as_uint(v.y) ^ tag;
          }
          if (!__any_sync(0xffffffffu, bad & 1)) break;
          spin_guard(t0);
        }
        if (t == 0) PROF_EV(11);
      }
      if (w == 0 && elect_one()) { mbar_expect_tx(bars + 8 * B_W, 8192); bulk_load(sb + OFF_D, dtab, 8192, bars + 8 * B_W); }
      asm volatile("barrier.cluster.wait.aligned;" ::: "memory");
      mbar_wait(bars + 8 * B_W, 0);
      mbar_wait(bars + 8 * B_HX, 0);
      if (t == 0) PROF_EV(12);
      const uint32_t dd = (sb & 0x3FFFF) >> 4;
      const uint64_t dF = d128((dd + (OFF_D >> 4)) | (512u << 16)), dI = d128((dd + (OFF_D >> 4)) | (1u << 16)), dA = d128((dd + (OFF_XB >> 4)) | (512u << 16));
      float az[32];
      const int zero = blockIdx.x >> 16;
      uint32_t pf[32];
#pragma unroll
      for (int mt = 0; mt < 2; mt++) {
        wg_fence();
        if (mt == 0) mma_ss64<0, 3, 0>(az, dA, dF);
        else mma_ss64<0, 3, 2>(az, dA + 512, dF, zero);
#pragma unroll
        for (int k = 1; k < 4; k++) mma_ss64<0, 3, 1>(az, dA + (mt * 512 + k * 128), dF + k * 128);
        wg_commit();
        wg_wait<0>();
        fence_regs<0, 32>(az);
#pragma unroll
        for (int i = 0; i < 16; i++) {
          const float wr = bf_lo(wf[16 * mt + i]), wi = bf_hi(wf[16 * mt + i]);
          pf[16 * mt + i] = pack_pin(fmaf(az[2 * i], wr, -az[2 * i + 1] * wi), fmaf(az[2 * i], wi, az[2 * i + 1] * wr));
        }
      }
      if (t == 0) PROF_EV(16);
      {
        const int m = lane >> 3, r = lane & 7;
        const int sl = 2 * (m >> 1) + ((r >> 1) & 1) + 4 * (r >> 2);
        const uint32_t a0 = sb + OFF_XB + (2 * w + (m & 1)) * 2048 + sl * 64;
        uint32_t pk[16];
#pragma unroll
        for (int mt = 0; mt < 3; mt++) {
          if (mt < 2) {
            wg_fence();
            mma_rs64<0, 0, 2>(az, pf[16 * mt], pf[16 * mt + 1], pf[16 * mt + 2], pf[16 * mt + 3], dI, mt ? (int)helper : zero);
#pragma unroll
            for (int k = 1; k < 4; k++) mma_rs64<0, 0, 1>(az, pf[16 * mt + 4 * k], pf[16 * mt + 4 * k + 1], pf[16 * mt + 4 * k + 2], pf[16 * mt + 4 * k + 3], dI + k * 2);
            wg_commit();
          }
          if (mt > 0 && !helper) {
#pragma unroll
            for (int i = 0; i < 4; i++) stsm4t(a0 + ((((mt - 1) * 2 + (r & 1)) ^ (sl >> 1)) << 4) + i * 512, pk[4 * i], pk[4 * i + 1], pk[4 * i + 2], pk[4 * i + 3]);
          }
          if (mt < 2) {
            wg_wait<0>();
            fence_regs<0, 32>(az);
#pragma unroll
            for (int i = 0; i < 16; i++) pk[i] = pack_pin(az[2 * i], az[2 * i + 1]);
          }
        }
      }
      if (helper) {
#pragma unroll
        for (int i = 0; i < 16; i++) {
          const int n = i >> 1, s0 = 8 * (n >> 1) + 2 * (n & 1) + (q & 1) + 4 * (q >> 1);
          if ((n & 1) == (int)(blockIdx.x & 1)) st_u2(ws->Ts + s0 * 64 + 16 * w + g + 8 * (i & 1), pack_bf16(az[2 * i], az[2 * i + 1]), tag);
        }
        __syncwarp();
        hint_add_if(lane == 0, &ws->cntH[0]);
        if (t == 0) { ws->epoch[blockIdx.x * 8] = ep + 1; PROF_EV(13); }
      } else {
        asm volatile("fence.proxy.async.shared::cta;" ::: "memory");
        __syncwarp();
        if (elect_one()) {
          if (t == 0) PROF_EV(17);
          if (SPACE) __nanosleep(SPACE * w);
          asm volatile("cp.async.bulk.tensor.3d.global.shared::cta.bulk_group [%0, {%2, %3, %4}], [%1];" ::"l"(&maps.ts), "r"(sb + OFF_XB + w * 4096),
                       "r"(32 * kg), "r"(0), "r"(8 * tn + 2 * w) : "memory");
          bulk_done_signal(&ws->cntT[32 * j]);
          asm volatile("mbarrier.arrive.shared::cluster.b64 _, [%0];" ::"r"(mapa(bars + 8 * B_RD0, rank ^ 1)) : "memory");
          if (t == 96) PROF_EV(13);
        }
        __syncwarp();
        if (j == 0) {
          hint_wait(&ws->cntH[0], (ep + 1) * 8u);
          const uint32_t t0 = (uint32_t)clock();
          float2 v;
          do { v = ld_x2((const float2*)ws->Ts + 2 * rb * 64 + t); spin_guard(t0); } while (__any_sync(0xffffffffu, (__float_as_uint(v.y) ^ tag) & 1));
          mbar_wait(bars + 8 * B_TL, 0);
          const uint32_t u = __float_as_uint(v.x);
          *(uint16_t*)(smem + OFF_T + t * 128 + ((t & 7) << 4)) = (uint16_t)u;
          *(uint16_t*)(smem + OFF_T + t * 128 + (((t & 7) ^ 1) << 4)) = (uint16_t)(u >> 16);
          asm volatile("fence.proxy.async.shared::cta;" ::: "memory");
          __syncwarp();
          mbar_arrive_if(lane == 0, bars + 8 * B_T);
        }
      }
    }
  } else {
    asm volatile("setmaxnreg.dec.sync.aligned.u32 24;");
    auto xf_load = [&](int q) {
      const uint32_t fb = bars + 8 * (B_FX + q);
      mbar_expect_tx(fb, U + 8192);
      tma3d(sb + q * U, &maps.x, fb, 64 * q, 0, 2 * rb);
      if (q >= 4) mbar_wait(bars + 8 * (B_FE + ((q - 4) >> 1)), 0);
      tma2d(sb + OFF_XB + (q & 3) * 8192, &maps.ft, fb, 64 * q, 64 * j);
    };
    if (elect_one()) {
      if (warp == 14) {
#pragma unroll
        for (int i = 0; i < B_FT; i++) mbar_init(bars + 8 * i, 1);
        asm volatile("fence.mbarrier_init.release.cluster;" ::: "memory");
        if (!helper) {
#pragma unroll 1
          for (int n = 0; n < 2; n++) {
            const uint32_t fb = bars + 8 * (B_FA + n);
            xf_load(2 * n); xf_load(2 * n + 1);
            mbar_expect_tx(fb, U);
            tma2d(sb + OFF_RING + n * U, &maps.g64, fb, f_full, 64 * n);
            tma2d(sb + OFF_RING + n * U + 8192, &maps.u64, fb, f_full, 64 * n);
          }
        }
      } else if (warp == 15) {
#pragma unroll
        for (int i = B_FT; i < NBAR; i++) mbar_init(bars + 8 * i, i < B_EA ? 1 : i < B_T ? 2 : 4);
#pragma unroll
        for (int i = 0; i < 8; i++) mbar_expect_tx(bars + 8 * (B_Z + i), U / 2);
        asm volatile("fence.mbarrier_init.release.cluster;" ::: "memory");
        asm volatile("fence.proxy.async.shared::cta;" ::: "memory");
      } else if (warp == 13 && !PF0) {
#pragma unroll
        for (int i = 1; i < 4; i++) asm volatile("prefetch.tensormap [%0];" ::"l"((const char*)&maps + i * 128) : "memory");
      }
    }
    __syncwarp();
    asm volatile("bar.arrive 0, 384;" ::: "memory");
    asm volatile("bar.arrive 4, 256;" ::: "memory");
    __syncwarp();
    asm volatile("barrier.cluster.arrive.relaxed.aligned;" ::: "memory");
    asm volatile("bar.sync 3, 128;" ::: "memory");
    if (warp == 15 && !helper) {
        mbar_wait(bars + 8 * B_FE, 0);
        const uint32_t tag = (ld_x1(&ws->epoch[blockIdx.x * 8]) + 1) & 1;
        const int c = lane >> 4, jj = 16 * blockIdx.x + (lane & 15), jm = (2048 - jj) & 2047;
        const unsigned short* pr = (const unsigned short*)w_r + 256 * c;
        const unsigned short* pi = (const unsigned short*)w_i + 256 * c;
        const float wr = 0.25f * (bf_lo(__ldg(pr + jj * 257)) + bf_lo(__ldg(pr + jm * 257)));
        const float wi = 0.25f * (bf_lo(__ldg(pi + jj * 257)) - bf_lo(__ldg(pi + jm * 257)));
        st_u2(ws->Wh + c * 2048 + jj, c ? pack_bf16(-wi, wr) : pack_bf16(wr, wi), tag);
        __syncwarp();
        hint_add_if(lane == 0, &ws->cntW[0]);
        mbar_wait(bars + 8 * B_XS, 0);
        const uint32_t t0 = (uint32_t)clock();
        uint4 v;
        do { v = ld_x4(ws->gate + rb * 128 + 4 * lane); spin_guard(t0); } while (__any_sync(0xffffffffu, ((v.x ^ tag) | (v.y ^ tag) | (v.z ^ tag) | (v.w ^ tag)) & 1));
        *(uint4*)(smem + OFF_G + lane * 16) = v;
        __syncwarp();
        mbar_arrive_if(lane < 4, bars + 8 * B_G);
      }
    if ((!helper || warp == 15) && elect_one()) {
      if (warp < 14) {
        const int p = warp - 12;
#pragma unroll 1
        for (int i = 4 + p; i < 14; i += 2) asm volatile("prefetch.tensormap [%0];" ::"l"((const char*)&maps + i * 128) : "memory");
#pragma unroll 1
        for (int n = 2; n < 31; n++) {
          const bool table = n == 4 || n >= 29;
          const bool half = n >= 17 && n < 21;
          const int q = n < 4 ? n : n < 17 ? n - 1 : n - 5;
          const CUtensorMap* m = table ? &maps.e : half ? &maps.g32 + p : &maps.g64 + p;
          const int c0 = table ? 0 : half ? f_half : f_full + 64 * (q >> 3);
          const int c1 = table ? (2 * rb + ((n & 1) ^ 1)) * 128 + 64 * p : half ? 128 * (n - 17) : 64 * (q & 7);
          const uint32_t fb = bars + 8 * (B_FA + (n & 3)), dst = sb + OFF_RING + (n & 3) * U + p * 8192;
          if (n < 4) mbar_wait(bars + 8 * (B_FE + n - 2), 0);
          else mbar_wait(bars + 8 * (B_EA + (n & 3)), ((n >> 2) & 1) ^ 1);
          tma2d(dst, m, fb, c0, c1);
          if (p == 0) mbar_expect_tx(fb, U);
        }
      } else if (warp == 15) {
        const unsigned ep1 = ld_x1(&ws->epoch[blockIdx.x * 8]) + 1;
        flag_wait(&ws->cntX[helper ? 0 : 32 * j], ep1 * 16u);
        PROF_EV(22);
        mbar_expect_tx(bars + 8 * B_HX, U);
        bulk_load(sb + OFF_XB, ws->X + (size_t)(helper ? 128 : kg * 8 + tn) * 8192, U, bars + 8 * B_HX);
        if (!helper) {
          flag_wait(&ws->cntT[32 * j], ep1 * 64u);
          PROF_EV(23);
          mbar_expect_tx(bars + 8 * B_TL, U);
          tma3d(sb + OFF_T, &maps.t, bars + 8 * B_TL, 64 * j, 0, 2 * rb);
#pragma unroll 1
          for (int i = 0; i < 3; i++) {
            flag_wait(&ws->cntP[32 * (rb * 8 + j) + i], ep1 * 8u);
            mbar_wait(bars + 8 * (B_PZ + (i == 0)), 0);
            if (i == 2) PROF_EV(26);
            mbar_expect_tx(bars + 8 * (B_HP + i), U);
            bulk_load(sb + (i ? (i - 1) * U : OFF_T), ws->part + (size_t)((rb * 8 + j) * 3 + i) * 1024, U, bars + 8 * (B_HP + i));
          }
          ws->epoch[blockIdx.x * 8] = ep1;
        }
      } else {
#pragma unroll 1
        for (int q = 4; q < 8; q++) xf_load(q);
        mbar_wait(bars + 8 * (B_FE + 2), 0);
        mbar_expect_tx(bars + 8 * B_E0, U);
        tma2d(sb + OFF_XB, &maps.e, bars + 8 * B_E0, 0, 2 * rb * 128);
        tma2d(sb + OFF_XB + 8192, &maps.e, bars + 8 * B_E0, 0, 2 * rb * 128 + 64);
#pragma unroll 1
        for (int h2 = 0; h2 < 2; h2++) {
          const int s0 = 2 * rb + h2, sg = (s0 & ~6) | ((s0 & 2) << 1) | ((s0 & 4) >> 1);
          mbar_wait(bars + 8 * (B_XS + h2), 0);
#pragma unroll 1
          for (int c = 0; c < 2; c++) {
            asm volatile("cp.async.bulk.tensor.4d.global.shared::cta.bulk_group [%0, {%2, %3, %4, %5}], [%1];" ::"l"(&maps.xs),
                         "r"(sb + OFF_XB + h2 * 8192 + c * 4096), "r"(0), "r"(sg), "r"(0), "r"(16 * j + 8 * c) : "memory");
            if (j == 0)
              asm volatile("cp.async.bulk.global.shared::cta.bulk_group [%0], [%1], 256;" ::"l"(ws->X + 128 * 8192 + c * 4096 + sg * 128),
                           "r"(sb + OFF_SP + h2 * 512 + c * 256) : "memory");
            if (SPACE && h2 + c < 2) __nanosleep(SPACE);
          }
        }
        bulk_done_signal(&ws->cntX[32 * j]);
        PROF_EV(20);
        if (rb < 8) asm volatile("cp.async.bulk.prefetch.tensor.2d.L2.global [%0, {%1, %2}];" ::"l"(&maps.g32 + (rb >> 2)), "r"(f_half), "r"(128 * (rb & 3)) : "memory");
        else asm volatile("cp.async.bulk.prefetch.tensor.2d.L2.global [%0, {%1, %2}];" ::"l"(&maps.d224), "r"(64 * (rb - 8)), "r"(224 * j) : "memory");
#pragma unroll 1
        for (int t = 0; t < 8; t++) {
          const int i = t < 3 ? t + 1 : t < 6 ? t - 2 : 0;
          const int col = 64 * (2 * ((q4 + i) & 3) + ((t < 3 || t == 6) ? 1 - rank : rank));
          const uint32_t fb = bars + 8 * (B_FT + (t & 3)), dst = sb + (t & 3) * TB;
          mbar_wait(bars + 8 * (B_ET + (t == 2 ? 3 : t & 3)), t >> 2);
          mbar_expect_tx(fb, TB);
          tma2d(dst, &maps.d224, fb, col, 224 * j);
          if (t < 2) mbar_wait(bars + 8 * (B_ET + t + 1), 0);
          tma2d(dst + 28672, &maps.ft, fb, col, 64 * j);
        }
      }
    }
  }
}

typedef CUresult (*EncodeFn)(CUtensorMap*, CUtensorMapDataType, cuuint32_t, void*, const cuuint64_t*, const cuuint64_t*, const cuuint32_t*,
                             const cuuint32_t*, CUtensorMapInterleave, CUtensorMapSwizzle, CUtensorMapL2promotion, CUtensorMapFloatOOBfill);

static void encode(EncodeFn f, CUtensorMap* m, const void* base, int rank, const cuuint64_t* dims, const cuuint64_t* strides, const cuuint32_t* box,
                   CUtensorMapSwizzle sw) {
  cuuint32_t es[5] = {1, 1, 1, 1, 1};
  f(m, CU_TENSOR_MAP_DATA_TYPE_BFLOAT16, rank, (void*)base, dims, strides, box, es, CU_TENSOR_MAP_INTERLEAVE_NONE, sw,
    CU_TENSOR_MAP_L2_PROMOTION_L2_128B, CU_TENSOR_MAP_FLOAT_OOB_FILL_NONE);
}

extern "C" void kernel_launch(void* const* d_in, const int* in_sizes, int n_in, void* d_out, int out_size) {
  (void)in_sizes; (void)n_in; (void)out_size;
  const __nv_bfloat16* x = (const __nv_bfloat16*)d_in[0];
  const __nv_bfloat16* w_r = (const __nv_bfloat16*)d_in[1];
  const __nv_bfloat16* w_i = (const __nv_bfloat16*)d_in[2];
  const __nv_bfloat16* Wg = (const __nv_bfloat16*)d_in[4];
  const __nv_bfloat16* Wu = (const __nv_bfloat16*)d_in[5];
  const __nv_bfloat16* Wd = (const __nv_bfloat16*)d_in[6];
  const __nv_bfloat16* gw = (const __nv_bfloat16*)d_in[7];

  void* fp = nullptr; cudaDriverEntryPointQueryResult qr;
  cudaGetDriverEntryPoint("cuTensorMapEncodeTiled", &fp, cudaEnableDefault, &qr);
  EncodeFn enc = (EncodeFn)fp;
  void *pFT, *pET, *pDT, *pW;
  cudaGetSymbolAddress(&pDT, g_DT); cudaGetSymbolAddress(&pW, g_work);
  void *pX = ((Work*)pW)->X, *pT = ((Work*)pW)->T;
  cudaGetSymbolAddress(&pFT, g_FT); cudaGetSymbolAddress(&pET, g_ET);

  Maps mp;
  const CUtensorMapSwizzle S128 = CU_TENSOR_MAP_SWIZZLE_128B, S64 = CU_TENSOR_MAP_SWIZZLE_64B;
  { cuuint64_t d[3] = {512, 64, 32}, s[2] = {32768, 1024}; cuuint32_t b[3] = {64, 64, 2}, b2[3] = {64, 16, 1};
    encode(enc, &mp.x, x, 3, d, s, b, S128); encode(enc, &mp.o, d_out, 3, d, s, b2, S128); }
  { cuuint64_t d[2] = {512, 512}, s[1] = {1024}; cuuint32_t b[2] = {64, 64}; encode(enc, &mp.ft, pFT, 2, d, s, b, S128); }
  { cuuint64_t d[4] = {128, 32, 2, 129}, s[3] = {256, 8192, 16384}; cuuint32_t b[4] = {128, 1, 2, 8}; encode(enc, &mp.xs, pX, 4, d, s, b, CU_TENSOR_MAP_SWIZZLE_NONE); }
  { cuuint64_t d[3] = {512, 32, 64}, s[2] = {65536, 1024}; cuuint32_t b[3] = {32, 32, 2}; encode(enc, &mp.ts, pT, 3, d, s, b, S64); }
  { cuuint64_t d[3] = {512, 64, 32}, s[2] = {1024, 65536}; cuuint32_t b[3] = {64, 64, 2}; encode(enc, &mp.t, pT, 3, d, s, b, S128); }
  { cuuint64_t d[2] = {64, 4096}, s[1] = {128}; cuuint32_t b[2] = {64, 64}; encode(enc, &mp.e, pET, 2, d, s, b, S128); }
  { cuuint64_t d[2] = {1792, 512}, s[1] = {3584}; cuuint32_t b[2] = {64, 64}, b2[2] = {32, 128};
    encode(enc, &mp.g64, Wg, 2, d, s, b, S128); encode(enc, &mp.u64, Wu, 2, d, s, b, S128);
    encode(enc, &mp.g32, Wg, 2, d, s, b2, S64); encode(enc, &mp.u32, Wu, 2, d, s, b2, S64); }
  { cuuint64_t d[2] = {512, 1792}, s[1] = {1024}; cuuint32_t b[2] = {64, 224}; encode(enc, &mp.d224, Wd, 2, d, s, b, S128); }
  { cuuint64_t d[4] = {264, 32, 8, 8}, s[3] = {32896, 512, 4112}; cuuint32_t b[4] = {24, 32, 2, 1};
    encode(enc, &mp.wr, w_r, 4, d, s, b, CU_TENSOR_MAP_SWIZZLE_NONE); encode(enc, &mp.wi, w_i, 4, d, s, b, CU_TENSOR_MAP_SWIZZLE_NONE); }

  cudaFuncSetAttribute(fused_kernel, cudaFuncAttributeMaxDynamicSharedMemorySize, SMEM_BYTES);
  fused_kernel<<<NCTA, 512, SMEM_BYTES>>>((Work*)pW, (const uint16_t*)pDT, w_r, w_i, gw, x, (const uint16_t*)pFT, Wg, Wu, mp);
}
```

```cpp
#include <cuda_runtime.h>
#include <cuda_bf16.h>
#include <cuda.h>
#include <stdint.h>

namespace tbl {
constexpr double PI = 3.14159265358979323846264338327950288;
constexpr double sin_s(double x) { double t = x, s = x; for (int n = 1; n < 12; n++) { t *= -x * x / ((2 * n) * (2 * n + 1)); s += t; } return s; }
constexpr double cos_s(double x) { double t = 1, s = 1; for (int n = 1; n < 12; n++) { t *= -x * x / ((2 * n - 1) * (2 * n)); s += t; } return s; }
constexpr double cos2048(int m) {
  m &= 2047; if (m > 1024) m = 2048 - m;
  bool neg = false; if (m > 512) { m = 1024 - m; neg = true; }
  double v = (m <= 256) ? cos_s(2 * PI * m / 2048) : sin_s(2 * PI * (512 - m) / 2048);
  return neg ? -v : v;
}
constexpr uint16_t to_bf16(double v) {
  if (v == 0) return 0;
  uint16_t s = 0; if (v < 0) { s = 0x8000; v = -v; }
  int e = 0; while (v >= 2) { v /= 2; e++; } while (v < 1) { v *= 2; e--; }
  double m = (v - 1) * 128; int mi = (int)m; double fr = m - mi;
  if (fr > 0.5 || (fr == 0.5 && (mi & 1))) mi++;
  if (mi == 128) { mi = 0; e++; }
  return (uint16_t)(s | ((e + 127) << 7) | mi);
}
struct CosT { uint16_t v[2048]; constexpr CosT() : v() { for (int i = 0; i < 2048; i++) v[i] = to_bf16(cos2048(i)); } };
struct alignas(1024) FT {
  uint16_t v[512 * 512];
  constexpr FT() : v() {
    CosT c;
    for (int r = 0; r < 512; r++) {
      int k = (r >> 4) * 8 + (r & 7), e = (r >> 3) & 1;
      int mul = 4 * k, add = e ? 512 : 0;
      if (k == 0 && e == 1) { mul = 1024; add = 0; }
      for (int d = 0; d < 512; d++) v[r * 512 + d] = c.v[(d * mul + add) & 2047];
    }
  }
};
struct alignas(1024) ET {
  uint16_t v[2048 * 128];
  constexpr ET() : v() {
    CosT c;
    for (int s = 0; s < 2048; s++)
      for (int j = 0; j < 64; j++) {
        const int o = (s & 31) * 8192 + (s >> 5) * 64 + j;
        v[o] = c.v[(s * j) & 2047]; v[o + 4096] = c.v[(s * j + 512) & 2047];
      }
  }
};
struct alignas(1024) DT {
  uint16_t v[64 * 64];
  constexpr DT() : v() {
    CosT c;
    for (int r = 0; r < 64; r++)
      for (int n = 0; n < 64; n++) {
        const int sg = r >> 1, s0 = (sg & ~6) | ((sg & 2) << 1) | ((sg & 4) >> 1), e = r & 1, f = n & 1;
        const int m = 64 * s0 * (n >> 1) + (e == f ? 0 : e ? -512 : 512);
        v[r * 64 + (((n >> 3) ^ (r & 7)) << 3) + (n & 7)] = c.v[m & 2047];
      }
  }
};
}

__device__ constexpr tbl::FT g_FT = tbl::FT();
__device__ constexpr tbl::ET g_ET = tbl::ET();
__device__ constexpr tbl::DT g_DT = tbl::DT();

struct alignas(1024) Work {
  unsigned epoch[132 * 8];
  unsigned cntX[8 * 32], cntT[8 * 32], cntP[128 * 32], cntW[32], cntH[32];
  alignas(16) float gate[16 * 128];
  alignas(16) uint2 Wh[2 * 2048];
  alignas(16) uint2 Ts[32 * 64];
  alignas(1024) uint16_t X[129 * 8192];
  alignas(1024) uint16_t T[32 * 64 * 512];
  alignas(1024) uint4 part[128 * 3 * 1024];
};
__device__ Work g_work;
#define PROF_EV(i) do {} while (0)
#define PROF_CK(i) do {} while (0)

__device__ __forceinline__ uint32_t smem_u32(const void* p) { return (uint32_t)__cvta_generic_to_shared(p); }
__device__ __forceinline__ void mbar_init(uint32_t bar, uint32_t cnt) { asm volatile("mbarrier.init.shared::cta.b64 [%0], %1;" ::"r"(bar), "r"(cnt)); }
__device__ __forceinline__ void mbar_expect_tx(uint32_t bar, uint32_t bytes) { asm volatile("mbarrier.arrive.expect_tx.shared::cta.b64 _, [%0], %1;" ::"r"(bar), "r"(bytes) : "memory"); }
__device__ __forceinline__ void mbar_arrive(uint32_t bar) { asm volatile("mbarrier.arrive.shared::cta.b64 _, [%0];" ::"r"(bar) : "memory"); }
__device__ __forceinline__ bool elect_one() {
  uint32_t p;
  asm volatile("{\n.reg .pred p;\nelect.sync _|p, 0xffffffff;\nselp.u32 %0, 1, 0, p;\n}" : "=r"(p));
  return p;
}
__device__ __forceinline__ void mbar_arrive_if(bool p, uint32_t bar) {
  asm volatile("{\n.reg .pred p;\nsetp.ne.b32 p, %1, 0;\n@p mbarrier.arrive.shared::cta.b64 _, [%0];\n}" ::"r"(bar), "r"((int)p) : "memory");
}
__device__ __forceinline__ void hint_add_if(bool p, unsigned* a) {
  asm volatile("{\n.reg .pred p;\nsetp.ne.b32 p, %1, 0;\n@p red.relaxed.gpu.global.add.u32 [%0], 1;\n}" ::"l"(a), "r"((int)p) : "memory");
}
__device__ __forceinline__ bool mbar_try(uint32_t bar, uint32_t parity) {
  uint32_t ok;
  asm volatile("{\n.reg .pred p;\nmbarrier.test_wait.parity.shared::cta.b64 p, [%1], %2;\nselp.u32 %0, 1, 0, p;\n}" : "=r"(ok) : "r"(bar), "r"(parity) : "memory");
  return ok;
}
__device__ __forceinline__ void mbar_wait(uint32_t bar, uint32_t parity) {
  asm volatile(
      "{\n.reg .pred p;\n.reg .u32 n;\nmov.u32 n, 0;\n"
      "W_LOOP:\nmbarrier.try_wait.parity.shared::cta.b64 p, [%0], %1;\n@p bra W_DONE;\n"
      "add.u32 n, n, 1;\nsetp.lt.u32 p, n, 0x40000;\n@p bra W_LOOP;\ntrap;\nW_DONE:\n}" ::"r"(bar), "r"(parity) : "memory");
}
__device__ __forceinline__ void bulk_load(uint32_t dst, const void* src, uint32_t bytes, uint32_t bar) {
  asm volatile("cp.async.bulk.shared::cluster.global.mbarrier::complete_tx::bytes [%0], [%1], %2, [%3];" ::"r"(dst), "l"(src), "r"(bytes), "r"(bar) : "memory");
}
__device__ __forceinline__ void cp16(uint32_t dst, const void* src) { asm volatile("cp.async.cg.shared.global [%0], [%1], 16;" ::"r"(dst), "l"(src) : "memory"); }
__device__ __forceinline__ void spin_guard(uint32_t t0) { if ((uint32_t)clock() - t0 > (1u << 30)) __trap(); }
__device__ __forceinline__ float tagf(float v, uint32_t tag) { return __uint_as_float((__float_as_uint(v) & ~1u) | tag); }
__device__ __forceinline__ float untag(float v) { return __uint_as_float(__float_as_uint(v) & ~1u); }
__device__ __forceinline__ void st_x2(float2* p, float a, float b) { asm volatile("st.relaxed.gpu.global.v2.f32 [%0], {%1,%2};" ::"l"(p), "f"(a), "f"(b) : "memory"); }
__device__ __forceinline__ float2 ld_x2(const float2* p) { float2 v; asm volatile("ld.relaxed.gpu.global.v2.f32 {%0,%1}, [%2];" : "=f"(v.x), "=f"(v.y) : "l"(p) : "memory"); return v; }
__device__ __forceinline__ void st_u2(uint2* p, uint32_t a, uint32_t b) { asm volatile("st.relaxed.gpu.global.v2.u32 [%0], {%1,%2};" ::"l"(p), "r"(a), "r"(b) : "memory"); }
__device__ __forceinline__ void prefetch2d(const CUtensorMap* m, int c0, int c1) { asm volatile("cp.async.bulk.prefetch.tensor.2d.L2.global [%0, {%1, %2}];" ::"l"(m), "r"(c0), "r"(c1) : "memory"); }
__device__ __forceinline__ void prefetch1d(const void* p, uint32_t bytes) { asm volatile("cp.async.bulk.prefetch.L2.global [%0], %1;" ::"l"(p), "r"(bytes) : "memory"); }
__device__ __forceinline__ uint32_t ld_x1(const void* p) { uint32_t v; asm volatile("ld.relaxed.gpu.global.u32 %0, [%1];" : "=r"(v) : "l"(p) : "memory"); return v; }
__device__ __forceinline__ uint4 ld_x4(const void* p) { uint4 v; asm volatile("ld.relaxed.gpu.global.v4.u32 {%0,%1,%2,%3}, [%4];" : "=r"(v.x), "=r"(v.y), "=r"(v.z), "=r"(v.w) : "l"(p) : "memory"); return v; }
__device__ __forceinline__ void st_x4(void* p, uint32_t a, uint32_t b, uint32_t c, uint32_t d) { asm volatile("st.relaxed.gpu.global.v4.u32 [%0], {%1,%2,%3,%4};" ::"l"(p), "r"(a), "r"(b), "r"(c), "r"(d) : "memory"); }
__device__ __forceinline__ uint32_t mapa(uint32_t a, uint32_t cta) { uint32_t r; asm volatile("mapa.shared::cluster.u32 %0, %1, %2;" : "=r"(r) : "r"(a), "r"(cta)); return r; }
__device__ __forceinline__ void stsm4t(uint32_t a, uint32_t r0, uint32_t r1, uint32_t r2, uint32_t r3) {
  asm volatile("stmatrix.sync.aligned.m8n8.x4.trans.shared.b16 [%0], {%1,%2,%3,%4};" ::"r"(a), "r"(r0), "r"(r1), "r"(r2), "r"(r3) : "memory");
}
__device__ __forceinline__ void hint_add(unsigned* p) { asm volatile("red.relaxed.gpu.global.add.u32 [%0], 1;" ::"l"(p) : "memory"); }
__device__ __forceinline__ void hint_wait(const unsigned* p, unsigned target) {
  const uint32_t t0 = (uint32_t)clock();
  while ((int)(ld_x1(p) - target) < 0) spin_guard(t0);
}
__device__ __forceinline__ void bulk_done_signal(unsigned* p) {
  asm volatile("cp.async.bulk.commit_group;\ncp.async.bulk.wait_group 0;\nfence.proxy.async.global;" ::: "memory");
  hint_add(p);
}
__device__ __forceinline__ void flag_wait(const unsigned* p, unsigned target) {
  hint_wait(p, target);
  asm volatile("fence.proxy.async.global;" ::: "memory");
}
__device__ __forceinline__ void tma2d(uint32_t dst, const CUtensorMap* m, uint32_t bar, int c0, int c1) {
  asm volatile("cp.async.bulk.tensor.2d.shared::cluster.global.mbarrier::complete_tx::bytes [%0], [%1, {%3, %4}], [%2];" ::"r"(dst), "l"(m), "r"(bar), "r"(c0), "r"(c1) : "memory");
}
__device__ __forceinline__ void tma3d(uint32_t dst, const CUtensorMap* m, uint32_t bar, int c0, int c1, int c2) {
  asm volatile("cp.async.bulk.tensor.3d.shared::cluster.global.mbarrier::complete_tx::bytes [%0], [%1, {%3, %4, %5}], [%2];" ::"r"(dst), "l"(m), "r"(bar), "r"(c0), "r"(c1), "r"(c2) : "memory");
}
__device__ __forceinline__ void tma4d(uint32_t dst, const CUtensorMap* m, uint32_t bar, int c0, int c1, int c2, int c3) {
  asm volatile("cp.async.bulk.tensor.4d.shared::cluster.global.mbarrier::complete_tx::bytes [%0], [%1, {%3, %4, %5, %6}], [%2];" ::"r"(dst), "l"(m), "r"(bar), "r"(c0), "r"(c1), "r"(c2), "r"(c3) : "memory");
}
__device__ __forceinline__ void wg_fence() { asm volatile("wgmma.fence.sync.aligned;" ::: "memory"); }
__device__ __forceinline__ void wg_commit() { asm volatile("wgmma.commit_group.sync.aligned;" ::: "memory"); }
template <int N> __device__ __forceinline__ void wg_wait() { asm volatile("wgmma.wait_group.sync.aligned %0;" ::"n"(N) : "memory"); }
template <int O, int N, int NN> __device__ __forceinline__ void fence_regs(float (&d)[NN]) {
#pragma unroll
  for (int i = 0; i < N; i++) asm volatile("" : "+f"(d[O + i])::"memory");
}
__device__ __forceinline__ uint32_t pack_bf16(float lo, float hi) {
  uint32_t r; asm("cvt.rn.bf16x2.f32 %0, %1, %2;" : "=r"(r) : "f"(hi), "f"(lo)); return r;
}
__device__ __forceinline__ uint32_t pack_pin(float lo, float hi) {
  uint32_t r; asm volatile("cvt.rn.bf16x2.f32 %0, %1, %2;" : "=r"(r) : "f"(hi), "f"(lo) : "memory"); return r;
}
__device__ __forceinline__ float bf_lo(uint32_t u) { return __uint_as_float(u << 16); }
__device__ __forceinline__ float bf_hi(uint32_t u) { return __uint_as_float(u & 0xffff0000u); }

__device__ __forceinline__ uint64_t d128(uint32_t lo) { uint64_t d; asm("mov.b64 %0, {%1, 0x40000040};" : "=l"(d) : "r"(lo)); return d; }
__device__ __forceinline__ uint64_t d64(uint32_t lo) { uint64_t d; asm("mov.b64 %0, {%1, 0x80000020};" : "=l"(d) : "r"(lo)); return d; }
template<int O,int TB,int ACC,int NN> __device__ __forceinline__ void mma_ss64(float (&d)[NN], uint64_t da, uint64_t db, int sd = 0){
  if constexpr (ACC == 1) asm volatile("wgmma.mma_async.sync.aligned.m64n64k16.f32.bf16.bf16 {%0,%1,%2,%3,%4,%5,%6,%7,%8,%9,%10,%11,%12,%13,%14,%15,%16,%17,%18,%19,%20,%21,%22,%23,%24,%25,%26,%27,%28,%29,%30,%31}, %32, %33, 1, 1, 1, %35, %34;"
   : "+f"(d[O+0]), "+f"(d[O+1]), "+f"(d[O+2]), "+f"(d[O+3]), "+f"(d[O+4]), "+f"(d[O+5]), "+f"(d[O+6]), "+f"(d[O+7]), "+f"(d[O+8]), "+f"(d[O+9]), "+f"(d[O+10]), "+f"(d[O+11]), "+f"(d[O+12]), "+f"(d[O+13]), "+f"(d[O+14]), "+f"(d[O+15]), "+f"(d[O+16]), "+f"(d[O+17]), "+f"(d[O+18]), "+f"(d[O+19]), "+f"(d[O+20]), "+f"(d[O+21]), "+f"(d[O+22]), "+f"(d[O+23]), "+f"(d[O+24]), "+f"(d[O+25]), "+f"(d[O+26]), "+f"(d[O+27]), "+f"(d[O+28]), "+f"(d[O+29]), "+f"(d[O+30]), "+f"(d[O+31])
   : "l"(da), "l"(db), "n"(TB & 1), "n"(TB >> 1));
  else if constexpr (ACC == 0) asm volatile("wgmma.mma_async.sync.aligned.m64n64k16.f32.bf16.bf16 {%0,%1,%2,%3,%4,%5,%6,%7,%8,%9,%10,%11,%12,%13,%14,%15,%16,%17,%18,%19,%20,%21,%22,%23,%24,%25,%26,%27,%28,%29,%30,%31}, %32, %33, 0, 1, 1, %35, %34;"
   : "=f"(d[O+0]), "=f"(d[O+1]), "=f"(d[O+2]), "=f"(d[O+3]), "=f"(d[O+4]), "=f"(d[O+5]), "=f"(d[O+6]), "=f"(d[O+7]), "=f"(d[O+8]), "=f"(d[O+9]), "=f"(d[O+10]), "=f"(d[O+11]), "=f"(d[O+12]), "=f"(d[O+13]), "=f"(d[O+14]), "=f"(d[O+15]), "=f"(d[O+16]), "=f"(d[O+17]), "=f"(d[O+18]), "=f"(d[O+19]), "=f"(d[O+20]), "=f"(d[O+21]), "=f"(d[O+22]), "=f"(d[O+23]), "=f"(d[O+24]), "=f"(d[O+25]), "=f"(d[O+26]), "=f"(d[O+27]), "=f"(d[O+28]), "=f"(d[O+29]), "=f"(d[O+30]), "=f"(d[O+31])
   : "l"(da), "l"(db), "n"(TB & 1), "n"(TB >> 1));
  else asm volatile("{\n.reg .pred p;\nsetp.ne.b32 p, %36, 0;\nwgmma.mma_async.sync.aligned.m64n64k16.f32.bf16.bf16 {%0,%1,%2,%3,%4,%5,%6,%7,%8,%9,%10,%11,%12,%13,%14,%15,%16,%17,%18,%19,%20,%21,%22,%23,%24,%25,%26,%27,%28,%29,%30,%31}, %32, %33, p, 1, 1, %35, %34;\n}"
   : "+f"(d[O+0]), "+f"(d[O+1]), "+f"(d[O+2]), "+f"(d[O+3]), "+f"(d[O+4]), "+f"(d[O+5]), "+f"(d[O+6]), "+f"(d[O+7]), "+f"(d[O+8]), "+f"(d[O+9]), "+f"(d[O+10]), "+f"(d[O+11]), "+f"(d[O+12]), "+f"(d[O+13]), "+f"(d[O+14]), "+f"(d[O+15]), "+f"(d[O+16]), "+f"(d[O+17]), "+f"(d[O+18]), "+f"(d[O+19]), "+f"(d[O+20]), "+f"(d[O+21]), "+f"(d[O+22]), "+f"(d[O+23]), "+f"(d[O+24]), "+f"(d[O+25]), "+f"(d[O+26]), "+f"(d[O+27]), "+f"(d[O+28]), "+f"(d[O+29]), "+f"(d[O+30]), "+f"(d[O+31])
   : "l"(da), "l"(db), "n"(TB & 1), "n"(TB >> 1), "r"(sd));
}
template<int O,int TB,int ACC,int NN> __device__ __forceinline__ void mma_rs64(float (&d)[NN], uint32_t a0, uint32_t a1, uint32_t a2, uint32_t a3, uint64_t db, int sd = 0){
  if constexpr (ACC == 1) asm volatile("wgmma.mma_async.sync.aligned.m64n64k16.f32.bf16.bf16 {%0,%1,%2,%3,%4,%5,%6,%7,%8,%9,%10,%11,%12,%13,%14,%15,%16,%17,%18,%19,%20,%21,%22,%23,%24,%25,%26,%27,%28,%29,%30,%31}, {%32,%33,%34,%35}, %36, 1, 1, 1, %37;"
   : "+f"(d[O+0]), "+f"(d[O+1]), "+f"(d[O+2]), "+f"(d[O+3]), "+f"(d[O+4]), "+f"(d[O+5]), "+f"(d[O+6]), "+f"(d[O+7]), "+f"(d[O+8]), "+f"(d[O+9]), "+f"(d[O+10]), "+f"(d[O+11]), "+f"(d[O+12]), "+f"(d[O+13]), "+f"(d[O+14]), "+f"(d[O+15]), "+f"(d[O+16]), "+f"(d[O+17]), "+f"(d[O+18]), "+f"(d[O+19]), "+f"(d[O+20]), "+f"(d[O+21]), "+f"(d[O+22]), "+f"(d[O+23]), "+f"(d[O+24]), "+f"(d[O+25]), "+f"(d[O+26]), "+f"(d[O+27]), "+f"(d[O+28]), "+f"(d[O+29]), "+f"(d[O+30]), "+f"(d[O+31])
   : "r"(a0), "r"(a1), "r"(a2), "r"(a3), "l"(db), "n"(TB));
  else if constexpr (ACC == 0) asm volatile("wgmma.mma_async.sync.aligned.m64n64k16.f32.bf16.bf16 {%0,%1,%2,%3,%4,%5,%6,%7,%8,%9,%10,%11,%12,%13,%14,%15,%16,%17,%18,%19,%20,%21,%22,%23,%24,%25,%26,%27,%28,%29,%30,%31}, {%32,%33,%34,%35}, %36, 0, 1, 1, %37;"
   : "=f"(d[O+0]), "=f"(d[O+1]), "=f"(d[O+2]), "=f"(d[O+3]), "=f"(d[O+4]), "=f"(d[O+5]), "=f"(d[O+6]), "=f"(d[O+7]), "=f"(d[O+8]), "=f"(d[O+9]), "=f"(d[O+10]), "=f"(d[O+11]), "=f"(d[O+12]), "=f"(d[O+13]), "=f"(d[O+14]), "=f"(d[O+15]), "=f"(d[O+16]), "=f"(d[O+17]), "=f"(d[O+18]), "=f"(d[O+19]), "=f"(d[O+20]), "=f"(d[O+21]), "=f"(d[O+22]), "=f"(d[O+23]), "=f"(d[O+24]), "=f"(d[O+25]), "=f"(d[O+26]), "=f"(d[O+27]), "=f"(d[O+28]), "=f"(d[O+29]), "=f"(d[O+30]), "=f"(d[O+31])
   : "r"(a0), "r"(a1), "r"(a2), "r"(a3), "l"(db), "n"(TB));
  else asm volatile("{\n.reg .pred p;\nsetp.ne.b32 p, %38, 0;\nwgmma.mma_async.sync.aligned.m64n64k16.f32.bf16.bf16 {%0,%1,%2,%3,%4,%5,%6,%7,%8,%9,%10,%11,%12,%13,%14,%15,%16,%17,%18,%19,%20,%21,%22,%23,%24,%25,%26,%27,%28,%29,%30,%31}, {%32,%33,%34,%35}, %36, p, 1, 1, %37;\n}"
   : "+f"(d[O+0]), "+f"(d[O+1]), "+f"(d[O+2]), "+f"(d[O+3]), "+f"(d[O+4]), "+f"(d[O+5]), "+f"(d[O+6]), "+f"(d[O+7]), "+f"(d[O+8]), "+f"(d[O+9]), "+f"(d[O+10]), "+f"(d[O+11]), "+f"(d[O+12]), "+f"(d[O+13]), "+f"(d[O+14]), "+f"(d[O+15]), "+f"(d[O+16]), "+f"(d[O+17]), "+f"(d[O+18]), "+f"(d[O+19]), "+f"(d[O+20]), "+f"(d[O+21]), "+f"(d[O+22]), "+f"(d[O+23]), "+f"(d[O+24]), "+f"(d[O+25]), "+f"(d[O+26]), "+f"(d[O+27]), "+f"(d[O+28]), "+f"(d[O+29]), "+f"(d[O+30]), "+f"(d[O+31])
   : "r"(a0), "r"(a1), "r"(a2), "r"(a3), "l"(db), "n"(TB), "r"(sd));
}
template<int O,int TB,int ACC,int NN> __device__ __forceinline__ void mma_ss128(float (&d)[NN], uint64_t da, uint64_t db, int sd = 0){
  if constexpr (ACC == 1) asm volatile("wgmma.mma_async.sync.aligned.m64n128k16.f32.bf16.bf16 {%0,%1,%2,%3,%4,%5,%6,%7,%8,%9,%10,%11,%12,%13,%14,%15,%16,%17,%18,%19,%20,%21,%22,%23,%24,%25,%26,%27,%28,%29,%30,%31,%32,%33,%34,%35,%36,%37,%38,%39,%40,%41,%42,%43,%44,%45,%46,%47,%48,%49,%50,%51,%52,%53,%54,%55,%56,%57,%58,%59,%60,%61,%62,%63}, %64, %65, 1, 1, 1, %67, %66;"
   : "+f"(d[O+0]), "+f"(d[O+1]), "+f"(d[O+2]), "+f"(d[O+3]), "+f"(d[O+4]), "+f"(d[O+5]), "+f"(d[O+6]), "+f"(d[O+7]), "+f"(d[O+8]), "+f"(d[O+9]), "+f"(d[O+10]), "+f"(d[O+11]), "+f"(d[O+12]), "+f"(d[O+13]), "+f"(d[O+14]), "+f"(d[O+15]), "+f"(d[O+16]), "+f"(d[O+17]), "+f"(d[O+18]), "+f"(d[O+19]), "+f"(d[O+20]), "+f"(d[O+21]), "+f"(d[O+22]), "+f"(d[O+23]), "+f"(d[O+24]), "+f"(d[O+25]), "+f"(d[O+26]), "+f"(d[O+27]), "+f"(d[O+28]), "+f"(d[O+29]), "+f"(d[O+30]), "+f"(d[O+31]), "+f"(d[O+32]), "+f"(d[O+33]), "+f"(d[O+34]), "+f"(d[O+35]), "+f"(d[O+36]), "+f"(d[O+37]), "+f"(d[O+38]), "+f"(d[O+39]), "+f"(d[O+40]), "+f"(d[O+41]), "+f"(d[O+42]), "+f"(d[O+43]), "+f"(d[O+44]), "+f"(d[O+45]), "+f"(d[O+46]), "+f"(d[O+47]), "+f"(d[O+48]), "+f"(d[O+49]), "+f"(d[O+50]), "+f"(d[O+51]), "+f"(d[O+52]), "+f"(d[O+53]), "+f"(d[O+54]), "+f"(d[O+55]), "+f"(d[O+56]), "+f"(d[O+57]), "+f"(d[O+58]), "+f"(d[O+59]), "+f"(d[O+60]), "+f"(d[O+61]), "+f"(d[O+62]), "+f"(d[O+63])
   : "l"(da), "l"(db), "n"(TB & 1), "n"(TB >> 1));
  else if constexpr (ACC == 0) asm volatile("wgmma.mma_async.sync.aligned.m64n128k16.f32.bf16.bf16 {%0,%1,%2,%3,%4,%5,%6,%7,%8,%9,%10,%11,%12,%13,%14,%15,%16,%17,%18,%19,%20,%21,%22,%23,%24,%25,%26,%27,%28,%29,%30,%31,%32,%33,%34,%35,%36,%37,%38,%39,%40,%41,%42,%43,%44,%45,%46,%47,%48,%49,%50,%51,%52,%53,%54,%55,%56,%57,%58,%59,%60,%61,%62,%63}, %64, %65, 0, 1, 1, %67, %66;"
   : "=f"(d[O+0]), "=f"(d[O+1]), "=f"(d[O+2]), "=f"(d[O+3]), "=f"(d[O+4]), "=f"(d[O+5]), "=f"(d[O+6]), "=f"(d[O+7]), "=f"(d[O+8]), "=f"(d[O+9]), "=f"(d[O+10]), "=f"(d[O+11]), "=f"(d[O+12]), "=f"(d[O+13]), "=f"(d[O+14]), "=f"(d[O+15]), "=f"(d[O+16]), "=f"(d[O+17]), "=f"(d[O+18]), "=f"(d[O+19]), "=f"(d[O+20]), "=f"(d[O+21]), "=f"(d[O+22]), "=f"(d[O+23]), "=f"(d[O+24]), "=f"(d[O+25]), "=f"(d[O+26]), "=f"(d[O+27]), "=f"(d[O+28]), "=f"(d[O+29]), "=f"(d[O+30]), "=f"(d[O+31]), "=f"(d[O+32]), "=f"(d[O+33]), "=f"(d[O+34]), "=f"(d[O+35]), "=f"(d[O+36]), "=f"(d[O+37]), "=f"(d[O+38]), "=f"(d[O+39]), "=f"(d[O+40]), "=f"(d[O+41]), "=f"(d[O+42]), "=f"(d[O+43]), "=f"(d[O+44]), "=f"(d[O+45]), "=f"(d[O+46]), "=f"(d[O+47]), "=f"(d[O+48]), "=f"(d[O+49]), "=f"(d[O+50]), "=f"(d[O+51]), "=f"(d[O+52]), "=f"(d[O+53]), "=f"(d[O+54]), "=f"(d[O+55]), "=f"(d[O+56]), "=f"(d[O+57]), "=f"(d[O+58]), "=f"(d[O+59]), "=f"(d[O+60]), "=f"(d[O+61]), "=f"(d[O+62]), "=f"(d[O+63])
   : "l"(da), "l"(db), "n"(TB & 1), "n"(TB >> 1));
  else asm volatile("{\n.reg .pred p;\nsetp.ne.b32 p, %68, 0;\nwgmma.mma_async.sync.aligned.m64n128k16.f32.bf16.bf16 {%0,%1,%2,%3,%4,%5,%6,%7,%8,%9,%10,%11,%12,%13,%14,%15,%16,%17,%18,%19,%20,%21,%22,%23,%24,%25,%26,%27,%28,%29,%30,%31,%32,%33,%34,%35,%36,%37,%38,%39,%40,%41,%42,%43,%44,%45,%46,%47,%48,%49,%50,%51,%52,%53,%54,%55,%56,%57,%58,%59,%60,%61,%62,%63}, %64, %65, p, 1, 1, %67, %66;\n}"
   : "+f"(d[O+0]), "+f"(d[O+1]), "+f"(d[O+2]), "+f"(d[O+3]), "+f"(d[O+4]), "+f"(d[O+5]), "+f"(d[O+6]), "+f"(d[O+7]), "+f"(d[O+8]), "+f"(d[O+9]), "+f"(d[O+10]), "+f"(d[O+11]), "+f"(d[O+12]), "+f"(d[O+13]), "+f"(d[O+14]), "+f"(d[O+15]), "+f"(d[O+16]), "+f"(d[O+17]), "+f"(d[O+18]), "+f"(d[O+19]), "+f"(d[O+20]), "+f"(d[O+21]), "+f"(d[O+22]), "+f"(d[O+23]), "+f"(d[O+24]), "+f"(d[O+25]), "+f"(d[O+26]), "+f"(d[O+27]), "+f"(d[O+28]), "+f"(d[O+29]), "+f"(d[O+30]), "+f"(d[O+31]), "+f"(d[O+32]), "+f"(d[O+33]), "+f"(d[O+34]), "+f"(d[O+35]), "+f"(d[O+36]), "+f"(d[O+37]), "+f"(d[O+38]), "+f"(d[O+39]), "+f"(d[O+40]), "+f"(d[O+41]), "+f"(d[O+42]), "+f"(d[O+43]), "+f"(d[O+44]), "+f"(d[O+45]), "+f"(d[O+46]), "+f"(d[O+47]), "+f"(d[O+48]), "+f"(d[O+49]), "+f"(d[O+50]), "+f"(d[O+51]), "+f"(d[O+52]), "+f"(d[O+53]), "+f"(d[O+54]), "+f"(d[O+55]), "+f"(d[O+56]), "+f"(d[O+57]), "+f"(d[O+58]), "+f"(d[O+59]), "+f"(d[O+60]), "+f"(d[O+61]), "+f"(d[O+62]), "+f"(d[O+63])
   : "l"(da), "l"(db), "n"(TB & 1), "n"(TB >> 1), "r"(sd));
}
template<int O,int TB,int ACC,int NN> __device__ __forceinline__ void mma_rs128(float (&d)[NN], uint32_t a0, uint32_t a1, uint32_t a2, uint32_t a3, uint64_t db, int sd = 0){
  if constexpr (ACC == 1) asm volatile("wgmma.mma_async.sync.aligned.m64n128k16.f32.bf16.bf16 {%0,%1,%2,%3,%4,%5,%6,%7,%8,%9,%10,%11,%12,%13,%14,%15,%16,%17,%18,%19,%20,%21,%22,%23,%24,%25,%26,%27,%28,%29,%30,%31,%32,%33,%34,%35,%36,%37,%38,%39,%40,%41,%42,%43,%44,%45,%46,%47,%48,%49,%50,%51,%52,%53,%54,%55,%56,%57,%58,%59,%60,%61,%62,%63}, {%64,%65,%66,%67}, %68, 1, 1, 1, %69;"
   : "+f"(d[O+0]), "+f"(d[O+1]), "+f"(d[O+2]), "+f"(d[O+3]), "+f"(d[O+4]), "+f"(d[O+5]), "+f"(d[O+6]), "+f"(d[O+7]), "+f"(d[O+8]), "+f"(d[O+9]), "+f"(d[O+10]), "+f"(d[O+11]), "+f"(d[O+12]), "+f"(d[O+13]), "+f"(d[O+14]), "+f"(d[O+15]), "+f"(d[O+16]), "+f"(d[O+17]), "+f"(d[O+18]), "+f"(d[O+19]), "+f"(d[O+20]), "+f"(d[O+21]), "+f"(d[O+22]), "+f"(d[O+23]), "+f"(d[O+24]), "+f"(d[O+25]), "+f"(d[O+26]), "+f"(d[O+27]), "+f"(d[O+28]), "+f"(d[O+29]), "+f"(d[O+30]), "+f"(d[O+31]), "+f"(d[O+32]), "+f"(d[O+33]), "+f"(d[O+34]), "+f"(d[O+35]), "+f"(d[O+36]), "+f"(d[O+37]), "+f"(d[O+38]), "+f"(d[O+39]), "+f"(d[O+40]), "+f"(d[O+41]), "+f"(d[O+42]), "+f"(d[O+43]), "+f"(d[O+44]), "+f"(d[O+45]), "+f"(d[O+46]), "+f"(d[O+47]), "+f"(d[O+48]), "+f"(d[O+49]), "+f"(d[O+50]), "+f"(d[O+51]), "+f"(d[O+52]), "+f"(d[O+53]), "+f"(d[O+54]), "+f"(d[O+55]), "+f"(d[O+56]), "+f"(d[O+57]), "+f"(d[O+58]), "+f"(d[O+59]), "+f"(d[O+60]), "+f"(d[O+61]), "+f"(d[O+62]), "+f"(d[O+63])
   : "r"(a0), "r"(a1), "r"(a2), "r"(a3), "l"(db), "n"(TB));
  else if constexpr (ACC == 0) asm volatile("wgmma.mma_async.sync.aligned.m64n128k16.f32.bf16.bf16 {%0,%1,%2,%3,%4,%5,%6,%7,%8,%9,%10,%11,%12,%13,%14,%15,%16,%17,%18,%19,%20,%21,%22,%23,%24,%25,%26,%27,%28,%29,%30,%31,%32,%33,%34,%35,%36,%37,%38,%39,%40,%41,%42,%43,%44,%45,%46,%47,%48,%49,%50,%51,%52,%53,%54,%55,%56,%57,%58,%59,%60,%61,%62,%63}, {%64,%65,%66,%67}, %68, 0, 1, 1, %69;"
   : "=f"(d[O+0]), "=f"(d[O+1]), "=f"(d[O+2]), "=f"(d[O+3]), "=f"(d[O+4]), "=f"(d[O+5]), "=f"(d[O+6]), "=f"(d[O+7]), "=f"(d[O+8]), "=f"(d[O+9]), "=f"(d[O+10]), "=f"(d[O+11]), "=f"(d[O+12]), "=f"(d[O+13]), "=f"(d[O+14]), "=f"(d[O+15]), "=f"(d[O+16]), "=f"(d[O+17]), "=f"(d[O+18]), "=f"(d[O+19]), "=f"(d[O+20]), "=f"(d[O+21]), "=f"(d[O+22]), "=f"(d[O+23]), "=f"(d[O+24]), "=f"(d[O+25]), "=f"(d[O+26]), "=f"(d[O+27]), "=f"(d[O+28]), "=f"(d[O+29]), "=f"(d[O+30]), "=f"(d[O+31]), "=f"(d[O+32]), "=f"(d[O+33]), "=f"(d[O+34]), "=f"(d[O+35]), "=f"(d[O+36]), "=f"(d[O+37]), "=f"(d[O+38]), "=f"(d[O+39]), "=f"(d[O+40]), "=f"(d[O+41]), "=f"(d[O+42]), "=f"(d[O+43]), "=f"(d[O+44]), "=f"(d[O+45]), "=f"(d[O+46]), "=f"(d[O+47]), "=f"(d[O+48]), "=f"(d[O+49]), "=f"(d[O+50]), "=f"(d[O+51]), "=f"(d[O+52]), "=f"(d[O+53]), "=f"(d[O+54]), "=f"(d[O+55]), "=f"(d[O+56]), "=f"(d[O+57]), "=f"(d[O+58]), "=f"(d[O+59]), "=f"(d[O+60]), "=f"(d[O+61]), "=f"(d[O+62]), "=f"(d[O+63])
   : "r"(a0), "r"(a1), "r"(a2), "r"(a3), "l"(db), "n"(TB));
  else asm volatile("{\n.reg .pred p;\nsetp.ne.b32 p, %70, 0;\nwgmma.mma_async.sync.aligned.m64n128k16.f32.bf16.bf16 {%0,%1,%2,%3,%4,%5,%6,%7,%8,%9,%10,%11,%12,%13,%14,%15,%16,%17,%18,%19,%20,%21,%22,%23,%24,%25,%26,%27,%28,%29,%30,%31,%32,%33,%34,%35,%36,%37,%38,%39,%40,%41,%42,%43,%44,%45,%46,%47,%48,%49,%50,%51,%52,%53,%54,%55,%56,%57,%58,%59,%60,%61,%62,%63}, {%64,%65,%66,%67}, %68, p, 1, 1, %69;\n}"
   : "+f"(d[O+0]), "+f"(d[O+1]), "+f"(d[O+2]), "+f"(d[O+3]), "+f"(d[O+4]), "+f"(d[O+5]), "+f"(d[O+6]), "+f"(d[O+7]), "+f"(d[O+8]), "+f"(d[O+9]), "+f"(d[O+10]), "+f"(d[O+11]), "+f"(d[O+12]), "+f"(d[O+13]), "+f"(d[O+14]), "+f"(d[O+15]), "+f"(d[O+16]), "+f"(d[O+17]), "+f"(d[O+18]), "+f"(d[O+19]), "+f"(d[O+20]), "+f"(d[O+21]), "+f"(d[O+22]), "+f"(d[O+23]), "+f"(d[O+24]), "+f"(d[O+25]), "+f"(d[O+26]), "+f"(d[O+27]), "+f"(d[O+28]), "+f"(d[O+29]), "+f"(d[O+30]), "+f"(d[O+31]), "+f"(d[O+32]), "+f"(d[O+33]), "+f"(d[O+34]), "+f"(d[O+35]), "+f"(d[O+36]), "+f"(d[O+37]), "+f"(d[O+38]), "+f"(d[O+39]), "+f"(d[O+40]), "+f"(d[O+41]), "+f"(d[O+42]), "+f"(d[O+43]), "+f"(d[O+44]), "+f"(d[O+45]), "+f"(d[O+46]), "+f"(d[O+47]), "+f"(d[O+48]), "+f"(d[O+49]), "+f"(d[O+50]), "+f"(d[O+51]), "+f"(d[O+52]), "+f"(d[O+53]), "+f"(d[O+54]), "+f"(d[O+55]), "+f"(d[O+56]), "+f"(d[O+57]), "+f"(d[O+58]), "+f"(d[O+59]), "+f"(d[O+60]), "+f"(d[O+61]), "+f"(d[O+62]), "+f"(d[O+63])
   : "r"(a0), "r"(a1), "r"(a2), "r"(a3), "l"(db), "n"(TB), "r"(sd));
}

#define NEARLY 0
#define XAHEAD 3
#define HEADN 6
#define WBATCH 1
#define WB 8
#define WSLEEP 20
#define XSPREAD 4
#define NOSEND 0
#define MSPLIT 3
#define PFALL 1
#define L2PF 1
#define STAG 0
#define EPF 2
#define XNB 2
#define FNB 0
#define GNB 0
#define TH 5
#define PF0 4
#define FSPLIT 1
#define MGLU 1
#define TS 9
#define TL 13
#define SPACE 40
#define WPF 1
#define WAFTER 7
#define WPACE 0
#define GATE_AT 4
#define TPACE 40
#define PFMODE 0
#define MAPMODE 1
template <int V> struct IC { static constexpr int value = V; };
struct Maps { CUtensorMap x, ft, g64, u64, e, wr, wi, xs, ts, t, g32, u32, d224, o; };

constexpr int NCTA = 130;
constexpr int U = 16384;
constexpr int TB = 36864;
constexpr int OFF_RING = 8 * U, OFF_Z = 12 * U, OFF_XB = 12 * U, OFF_T = 13 * U, OFF_D = OFF_T;
constexpr int OFF_BAR = 14 * U, OFF_SP = OFF_BAR + 512, OFF_G = OFF_SP + 1024 + 128;
constexpr int SMEM_BYTES = OFF_G + 512;
constexpr int B_FX = 0, B_FA = 8, B_FT = 12, B_Z = 16, B_W = 24, B_HX = 25, B_TL = 26, B_HP = 27, B_WR = 30, B_E0 = 34;
constexpr int B_EA = 35, B_ET = 39, B_PZ = 43, B_RDY = 45, B_FE = 46;
constexpr int B_T = 50, B_XS = 51, B_G = 53, B_RD0 = 54, NBAR = 55;
__host__ __device__ constexpr int rslot(int n) { return n & 3; }
__host__ __device__ constexpr int rpar(int n) { return (n >> 2) & 1; }

__global__ void __cluster_dims__(2, 1, 1) __launch_bounds__(512, 1)
fused_kernel(Work* __restrict__ ws, const uint16_t* __restrict__ dtab, const __nv_bfloat16* __restrict__ w_r, const __nv_bfloat16* __restrict__ w_i,
             const __nv_bfloat16* __restrict__ gate_w, const __nv_bfloat16* __restrict__ x, const uint16_t* __restrict__ ftab,
             const __nv_bfloat16* __restrict__ Wg, const __nv_bfloat16* __restrict__ Wu, const __grid_constant__ Maps maps) {
  extern __shared__ __align__(1024) uint8_t smem[];
  if (threadIdx.x < 32 && elect_one()) {
#pragma unroll
    for (int i = 0; i < PF0; i++) asm volatile("prefetch.tensormap [%0];" ::"l"((const char*)&maps + i * 128) : "memory");
  }
  const uint32_t sb = smem_u32(smem);
  const uint32_t bars = sb + OFF_BAR;
  const int tid = threadIdx.x, lane = tid & 31;
  const int warp = __shfl_sync(0xffffffffu, tid >> 5, 0);
  const bool helper = blockIdx.x >= 128;
  const int cl = (blockIdx.x >> 1) & 63, rank = blockIdx.x & 1;
  const int q4 = (cl & 1) | ((cl >> 2) & 2), rb = ((cl >> 1) & 3) | ((cl >> 4) << 2);
  const int j = 2 * q4 + rank;
  const int f_full = 448 * q4 + (rank ? 256 : 0);
  const int f_half = 448 * q4 + (rank ? 224 : 192);
  const int kg = 2 * j + (rb >> 3), tn = rb & 7;

  if (tid == 64) { PROF_EV(0); PROF_CK(40); }
  if (warp < 8) {
    if (!helper) {
      if (tid < 16 * XNB) {
        const int r = 16 * j + (tid & 15);
        asm volatile("prefetch.global.L2 [%0];" ::"l"(x + (size_t)(2 * rb + (r >> 6) + 32 * (r & 63)) * 512 + 64 * (tid >> 4)));
      } else if (tid >= 128 && tid < 128 + 4 * FNB) {
        asm volatile("prefetch.global.L2 [%0];" ::"l"(ftab + (64 * j + 4 * rb + (tid & 3)) * 512 + 64 * ((tid - 128) >> 2)));
      } else if (tid >= 192 && tid < 192 + 8 * GNB) {
        asm volatile("prefetch.global.L2 [%0];" ::"l"(((tid & 4) ? Wu : Wg) + (size_t)(64 * ((tid - 192) >> 3) + 4 * rb + (tid & 3)) * 1792 + f_full));
      }
    }
    asm volatile("barrier.cluster.arrive.relaxed.aligned;" ::: "memory");
    asm volatile("setmaxnreg.inc.sync.aligned.u32 192;");
    if (!helper) {
      const int wg = warp >> 2, w = warp & 3, g = lane >> 2;
      const bool elect = (tid & 127) == 0;
      float cX[32], cA[64], cB[64], cC[64], ci[64], ct[64];
      const int zero = blockIdx.x >> 16;
      uint32_t h[56], yf[16];
      const uint32_t d0 = (sb & 0x3FFFF) >> 4;
      const uint32_t dK = d0 | (1u << 16), dN = d0 | (512u << 16);
      const uint32_t dX = dK + wg * 512;
      constexpr uint32_t RING = OFF_RING >> 4;
      auto waitA = [&](int n) { mbar_wait(bars + 8 * (B_FA + rslot(n)), rpar(n)); };
      auto freeA = [&](int n) { mbar_arrive_if(elect, bars + 8 * (B_EA + rslot(n))); };
      auto nop = [] {};

      asm volatile("bar.sync 0, 384;" ::: "memory");
#pragma unroll 1
      for (int i = 0; i < 4; i++) {
        const uint64_t dx = d128(dX + i * 2048), df = d128(dK + (OFF_XB >> 4) + (i & 1) * 1024);
        mbar_wait(bars + 8 * (B_FX + 2 * i), 0);
        wg_fence();
        mma_ss64<0, 0, 2>(cX, df, dx, i);
        mma_ss64<0, 0, 1>(cX, df + 2, dx + 2);
        wg_commit(); wg_wait<1>();
        mbar_arrive_if(elect && i, bars + 8 * (B_EA + rslot(i - 1)));
        mma_ss64<0, 0, 1>(cX, df + 4, dx + 4);
        mma_ss64<0, 0, 1>(cX, df + 6, dx + 6);
        if (i == 0 && tid == 0) PROF_EV(1);
        mbar_wait(bars + 8 * (B_FX + 2 * i + 1), 0);
        wg_fence();
#pragma unroll
        for (int k = 0; k < 4; k++) mma_ss64<0, 0, 1>(cX, df + (512 + k * 2), dx + (1024 + k * 2));
        wg_commit();
        waitA(i);
        wg_fence();
        const uint64_t da = d128(dX + i * 1024), db = d128(dN + RING + i * 1024);
        mma_ss128<0, 1, 2>(cA, da, db, i);
        wg_commit(); wg_wait<1>();
        mbar_arrive_if(elect, bars + 8 * (B_FE + i));
#pragma unroll
        for (int k = 1; k < 4; k++) mma_ss128<0, 1, 1>(cA, da + k * 2, db + k * 128);
        wg_commit();
      }
      fence_regs<0, 32>(cX);
#pragma unroll
      for (int e = 0; e < 16; e++) yf[e] = pack_pin(cX[2 * e], cX[2 * e + 1]);
      if (tid == 0) { PROF_EV(2); PROF_CK(42); }
      {
        waitA(4); mbar_wait(bars + 8 * B_E0, 0);
        const uint64_t de = d128(dN + (wg ? RING : OFF_XB >> 4));
        wg_fence();
        mma_rs128<0, 1, 0>(cB, yf[0], yf[1], yf[2], yf[3], de);
        wg_commit();
        wg_wait<1>();
        freeA(3);
#pragma unroll
        for (int k = 1; k < 4; k++) mma_rs128<0, 1, 1>(cB, yf[4 * k], yf[4 * k + 1], yf[4 * k + 2], yf[4 * k + 3], de + k * 128);
        wg_commit();
      }
      bool rel = false;
      auto acquire = [&](int n) {
        rel = elect;
        if (!mbar_try(bars + 8 * (B_FA + rslot(n)), rpar(n))) { wg_wait<0>(); freeA(n - 1); rel = false; waitA(n); }
      };
      auto freeP = [&](int n) { mbar_arrive_if(rel, bars + 8 * (B_EA + rslot(n - 1))); };
      auto ffn_step = [&](auto first, auto split, float (&acc)[64], int n, int kb, auto done, auto work) {
        constexpr int SPLIT = decltype(split)::value;
        acquire(n);
        wg_fence();
        const uint64_t dx = d128(dX + kb * 1024), db = d128(dN + RING + rslot(n) * 1024);
        mma_ss128<0, 1, decltype(first)::value>(acc, dx, db, kb);
#pragma unroll
        for (int k = 1; k < SPLIT; k++) mma_ss128<0, 1, 1>(acc, dx + k * 2, db + k * 128);
        wg_commit();
        work();
        wg_wait<1>();
        freeP(n);
        done();
        if (SPLIT < 4) {
          wg_fence();
#pragma unroll
          for (int k = SPLIT; k < 4; k++) mma_ss128<0, 1, 1>(acc, dx + k * 2, db + k * 128);
          wg_commit();
        }
      };
      {
        const int s0 = 2 * rb + wg, kr = 2 * ((s0 & 1) | ((s0 & 4) >> 1));
        const int m = lane >> 3, r = lane & 7;
        const uint32_t a0 = sb + OFF_XB + wg * 8192 + (((w >> 1) * 8 + (m >> 1)) * 2 + (w & 1)) * 256 + (m & 1) * 128 + ((r ^ (kr + (m & 1))) << 4);
        ffn_step(IC<1>(), IC<4>(), cA, 5, 4, [&] { fence_regs<0, 64>(cB); }, nop);
        asm volatile("bar.sync 5, 256;" ::: "memory");
        auto stage = [&](int i) {
          stsm4t(a0 + i * 1024, pack_bf16(cB[8 * i] - cB[34 + 8 * i], cB[8 * i + 1] - cB[35 + 8 * i]),
                 pack_bf16(cB[32 + 8 * i] + cB[8 * i + 2], cB[33 + 8 * i] + cB[8 * i + 3]),
                 pack_bf16(cB[8 * i + 4] - cB[38 + 8 * i], cB[8 * i + 5] - cB[39 + 8 * i]),
                 pack_bf16(cB[36 + 8 * i] + cB[8 * i + 6], cB[37 + 8 * i] + cB[8 * i + 7]));
          if (j == 0 && w == 0) {
            const uint32_t a1 = r ? sb + OFF_SP + 1024 : sb + OFF_SP + wg * 512 + (m & 1) * 256 + (m >> 1) * 128;
#pragma unroll
            for (int n = 2 * i; n < 2 * i + 2; n++)
              asm volatile("stmatrix.sync.aligned.m8n8.x4.shared.b16 [%0], {%1,%2,%3,%4};" ::"r"(a1 + ((n ^ (kr + (m >> 1)) ^ r) << 4)),
                           "r"(pack_bf16(cB[4 * n], cB[4 * n + 1])), "r"(pack_bf16(cB[4 * n + 2], cB[4 * n + 3])),
                           "r"(pack_bf16(cB[32 + 4 * n], cB[33 + 4 * n])), "r"(pack_bf16(cB[34 + 4 * n], cB[35 + 4 * n])) : "memory");
          }
        };
        auto publish = [&] {
          asm volatile("fence.proxy.async.shared::cta;" ::: "memory");
          __syncwarp();
          mbar_arrive_if(lane == 0, bars + 8 * (B_XS + wg));
          if (tid == 0) PROF_EV(3);
        };
        stage(0);
        ffn_step(IC<1>(), IC<FSPLIT>(), cA, 6, 5, nop, nop);
        stage(1);
        ffn_step(IC<1>(), IC<FSPLIT>(), cA, 7, 6, nop, nop);
        stage(2);
        ffn_step(IC<1>(), IC<2>(), cA, 8, 7, [&] { stage(3); }, nop);
        publish();
      }
      float g0 = 0.f, g1 = 0.f;
      uint32_t tag = 0;
      uint32_t ob[2] = {0, 0};
      auto glu = [&](auto& acc, int half, int ho, int i0, int i1) {
#pragma unroll
        for (int i = i0; i < i1; i++)
          asm volatile("{\n.reg .b32 a, b;\ncvt.rn.relu.bf16x2.f32 a, %2, %1;\ncvt.rn.bf16x2.f32 b, %4, %3;\nmul.rn.bf16x2 a, a, b;\nmul.rn.bf16x2 %0, a, %5;\n}"
                       : "=r"(h[ho + i]) : "f"(acc[2 * i]), "f"(acc[2 * i + 1]), "f"(acc[half + 2 * i]), "f"(acc[half + 1 + 2 * i]), "r"(ob[i & 1]) : "memory");
      };
      ffn_step(IC<2>(), IC<1>(), cB, 9, zero, nop, nop);
#pragma unroll 1
      for (int kb = 1; kb < 8; kb++)
        ffn_step(IC<1>(), IC<FSPLIT>(), cB, 9 + kb, kb, nop, [&] {
          if (kb == 4 + 2 * wg) {
            mbar_wait(bars + 8 * B_G, 0);
            const uint32_t gb0 = *(const uint32_t*)(smem + OFF_G + (wg * 64 + w * 16 + g) * 4), gb1 = *(const uint32_t*)(smem + OFF_G + (wg * 64 + w * 16 + g + 8) * 4);
            tag = gb0 & 1; g0 = __uint_as_float(gb0 & ~1u); g1 = __uint_as_float(gb1 & ~1u);
            ob[0] = pack_bf16(1.0f - g0, 1.0f - g0); ob[1] = pack_bf16(1.0f - g1, 1.0f - g1);
            glu(cA, 32, 0, 0, 16);
          }
        });
      if (tid == 0) { PROF_EV(4); PROF_CK(43); }
      auto m_step = [&](auto first, int i) {
        acquire(17 + i);
        wg_fence();
        const uint64_t dx = d128(dX + i * 2048), dm = d64(dN + RING + rslot(17 + i) * 1024);
        mma_ss64<0, 1, decltype(first)::value>(ct, dx, dm);
#pragma unroll
        for (int k = 1; k < MSPLIT; k++) mma_ss64<0, 1, 1>(ct, dx + ((k >> 2) * 1024 + (k & 3) * 2), dm + k * 64);
        wg_commit();
        wg_wait<1>();
        freeP(17 + i);
        wg_fence();
#pragma unroll
        for (int k = MSPLIT; k < 8; k++) mma_ss64<0, 1, 1>(ct, dx + ((k >> 2) * 1024 + (k & 3) * 2), dm + k * 64);
        wg_commit();
      };
      m_step(IC<0>(), 0);
#pragma unroll 1
      for (int i = 1; i < 5; i++) {
        if (i == 1 + 2 * wg) glu(cB, 32, 16, 0, 16);
        if (i < 4) m_step(IC<1>(), i);
      }
      if (tid == 0) { PROF_EV(5); PROF_CK(44); }
      ffn_step(IC<0>(), IC<1>(), cC, 21, 0, nop, nop);
#pragma unroll 1
      for (int kb = 1; kb < 8; kb++)
        ffn_step(IC<1>(), IC<FSPLIT>(), cC, 21 + kb, kb, [&] { mbar_arrive_if(elect && !(kb & 1), bars + 8 * (B_ET + (kb >> 1) - 1)); }, [&] {
          if (kb == 1 + wg) glu(ct, 16, 48, 0, 8);
        });

      auto twait = [&](uint32_t bar, uint32_t par, int) { mbar_wait(bar, par); };
      auto tr = [] {};
      const int fo = warp * 128 + lane;
      auto fetch = [&](uint4 (&pv)[4], int z) {
        twait(bars + 8 * (z < 4 ? B_Z + 2 * z + wg : B_HP + z - 4), 0, 8 + z);
        const uint8_t* src = smem + (z < 4 ? OFF_Z - z * U : z == 4 ? OFF_T : (z - 5) * U) + fo * 16;
#pragma unroll
        for (int i = 0; i < 4; i++) pv[i] = *(const uint4*)(src + i * 512);
      };
      const uint32_t peerZ = mapa(sb + OFF_Z + fo * 16, rank ^ 1), peerB = mapa(bars + 8 * (B_Z + wg), rank ^ 1);
      auto tile_mma = [&](auto off, int t, int k0, int k1, int init) {
        constexpr int O = decltype(off)::value;
        const uint64_t db = d128(dN + (t & 3) * (TB >> 4)), dw = db + rank * 256, dm = db + (rank ? 0 : 1536);
#pragma unroll
        for (int k = k0; k < k1; k++) {
          if (k == 0) mma_rs64<O, 1, 2>(ct, h[0], h[1], h[2], h[3], dw, init);
          else if (k < 14) mma_rs64<O, 1, 1>(ct, h[4 * k], h[4 * k + 1], h[4 * k + 2], h[4 * k + 3], k < 12 ? dw + k * 128 : dm + (k - 12) * 128);
          else mma_rs64<O, 1, 1>(ct, yf[4 * k - 56], yf[4 * k - 55], yf[4 * k - 54], yf[4 * k - 53], db + k * 128);
        }
      };
      auto tile = [&](auto off, int t) {
        constexpr int P = 32 - decltype(off)::value;
        const bool grid = t >= 4 && t < 7, pre = t != 1 && t != 5;
        const int zo = grid ? t - 4 : t == 7 ? 3 : t - 1, z = t - 2;
        const int owner = rb * 8 + 2 * ((q4 + zo + 1) & 3) + rank;
        const uint32_t src = sb + (z < 4 ? OFF_Z - z * U : z == 4 ? OFF_T : (z - 5) * U) + fo * 16;
        const uint32_t stg = sb + OFF_Z - zo * U + warp * 2048;
        twait(bars + 8 * (B_FT + (t & 3)), t >> 2, t);
        wg_fence();
        tile_mma(off, t, 0, TH, t >= 3 && t != 6);
        wg_commit();
        wg_wait<1>();
        mbar_arrive_if(elect && t < 6, bars + 8 * (B_ET + t - 1));
        if (t < 3) twait(bars + 8 * (t == 1 ? B_RD0 : B_RDY), 0, 14 + t);
        fence_regs<P, 32>(ct);
        uint32_t pk[16];
#pragma unroll
        for (int i = 0; i < 16; i++) pk[i] = pack_bf16(ct[P + 2 * i], ct[P + 2 * i + 1]);
        if (grid) {
#pragma unroll
          for (int i = 0; i < 4; i++)
            asm volatile("st.shared.v4.u32 [%0], {%1,%2,%3,%4};" ::"r"(stg + i * 512 + lane * 16), "r"(pk[4 * i]), "r"(pk[4 * i + 1]), "r"(pk[4 * i + 2]), "r"(pk[4 * i + 3]) : "memory");
        } else {
#pragma unroll
          for (int i = 0; i < 2; i++)
            asm volatile("st.async.weak.shared::cluster.mbarrier::complete_tx::bytes.v4.b32 [%0], {%1,%2,%3,%4}, [%5];" ::"r"(peerZ - zo * U + i * 512),
                         "r"(pk[4 * i]), "r"(pk[4 * i + 1]), "r"(pk[4 * i + 2]), "r"(pk[4 * i + 3]), "r"(peerB + 16 * zo) : "memory");
        }
        wg_fence();
        tile_mma(off, t, TH, TS, 0);
        wg_commit();
        if (grid) {
          asm volatile("fence.proxy.async.shared::cta;" ::: "memory");
          __syncwarp();
          if (elect_one())
            asm volatile("cp.async.bulk.global.shared::cta.bulk_group [%0], [%1], 2048;" ::"l"(ws->part + (size_t)(owner * 3 + zo) * 1024 + warp * 128), "r"(stg) : "memory");
        } else {
#pragma unroll
          for (int i = 2; i < 4; i++)
            asm volatile("st.async.weak.shared::cluster.mbarrier::complete_tx::bytes.v4.b32 [%0], {%1,%2,%3,%4}, [%5];" ::"r"(peerZ - zo * U + i * 512),
                         "r"(pk[4 * i]), "r"(pk[4 * i + 1]), "r"(pk[4 * i + 2]), "r"(pk[4 * i + 3]), "r"(peerB + 16 * zo) : "memory");
        }
        wg_fence();
        tile_mma(off, t, TS, TL, 0);
        wg_commit();
        if (pre) twait(bars + 8 * (z < 4 ? B_Z + 2 * z + wg : B_HP + z - 4), 0, 8 + z);
        wg_fence();
        uint4 pv[4];
#pragma unroll
        for (int i = 0; i < 4; i++) {
          asm volatile("{\n.reg .pred p;\nsetp.ne.b32 p, %5, 0;\n@p ld.shared.v4.u32 {%0,%1,%2,%3}, [%4];\n}"
                       : "=r"(pv[i].x), "=r"(pv[i].y), "=r"(pv[i].z), "=r"(pv[i].w) : "r"(src + i * 512), "r"((int)pre) : "memory");
          tile_mma(off, t, TL + i, i < 3 ? TL + 1 + i : 18, 0);
        }
        wg_commit();
        if (grid && elect_one()) bulk_done_signal(&ws->cntP[32 * owner + zo]);
        if (pre) {
#pragma unroll
          for (int i = 0; i < 4; i++) {
            const uint32_t a[4] = {pv[i].x, pv[i].y, pv[i].z, pv[i].w};
#pragma unroll
            for (int e = 0; e < 4; e++) { ct[P + 8 * i + 2 * e] = bf_lo(a[e]); ct[P + 8 * i + 2 * e + 1] = bf_hi(a[e]); }
          }
        }
      };
      asm volatile("barrier.cluster.wait.aligned;" ::: "memory");
      twait(bars + 8 * B_FT, 0, 0);
      wg_fence();
      tile_mma(IC<0>(), 0, 0, 5, zero);
      wg_commit();
      wg_wait<1>();
      mbar_arrive_if(elect, bars + 8 * (B_ET + 3));
      glu(cC, 32, 32, 0, 8);
      waitA(29 + wg);
      wg_fence();
      tile_mma(IC<0>(), 0, 5, 8, 0);
      tile_mma(IC<0>(), 0, 12, 14, 0);
      wg_commit();
      glu(cC, 32, 32, 8, 16);
      if (tid == 0) PROF_EV(6);
      if (tid == 128) PROF_EV(27);
      mbar_wait(bars + 8 * (j == 0 ? B_T : B_TL), 0);
      if (tid == 0) { PROF_EV(7); PROF_CK(45); }
      wg_fence();
      {
        const uint64_t dt = d128(dN + (OFF_T >> 4) + wg * 512), de = d128(dK + RING + (1 + wg) * 1024);
        mma_ss64<0, 1, 0>(ci, de, dt);
        mma_ss64<32, 1, 0>(ci, de + 512, dt);
#pragma unroll
        for (int k = 1; k < 4; k++) {
          mma_ss64<0, 1, 1>(ci, de + k * 2, dt + k * 128);
          mma_ss64<32, 1, 1>(ci, de + (512 + k * 2), dt + k * 128);
        }
        wg_commit();
      }
      tile_mma(IC<0>(), 0, 8, 12, 0);
      wg_commit();
      wg_wait<1>();
      if (elect) asm volatile("mbarrier.arrive.shared::cluster.b64 _, [%0];" ::"r"(mapa(bars + 8 * B_RDY, rank ^ 1)) : "memory");
      mbar_arrive_if(elect, bars + 8 * (B_PZ + 1));
      fence_regs<0, 64>(ci);
#pragma unroll
      for (int i = 0; i < 16; i++) {
        const float gg = ((i & 1) ? g1 : g0) * (2.0f / (2048.0f * 512.0f));
        if (i & 2) yf[i] = pack_pin((ci[2 * i] - ci[28 + 2 * i]) * gg, (ci[2 * i + 1] - ci[29 + 2 * i]) * gg);
        else yf[i] = pack_pin((ci[2 * i] + ci[36 + 2 * i]) * gg, (ci[2 * i + 1] + ci[37 + 2 * i]) * gg);
      }
      wg_fence();
      tile_mma(IC<0>(), 0, 14, 18, 0);
      wg_commit();
      if (tid == 0) PROF_EV(8);
      if (tid == 128) PROF_EV(28);
#pragma unroll 1
      for (int t = 1;; t += 2) {
        tile(IC<32>(), t);
        if (t == 7) break;
        tile(IC<0>(), t + 1);
      }
      if (tid == 0) { PROF_EV(9); PROF_CK(46); }
      if (tid == 128) PROF_EV(29);
      {
        float (&sum)[64] = ct;
        uint4 p2[4], p3[4];
        fetch(p3, 3);
        if (tid == 0) PROF_EV(25);
        fetch(p2, 6);
        if (tid == 0) PROF_EV(24);
#pragma unroll
        for (int i = 0; i < 4; i++) {
          const uint32_t b[4] = {p2[i].x, p2[i].y, p2[i].z, p2[i].w}, c[4] = {p3[i].x, p3[i].y, p3[i].z, p3[i].w};
#pragma unroll
          for (int e = 0; e < 4; e++) {
            sum[8 * i + 2 * e] += bf_lo(c[e]) + bf_lo(b[e]);
            sum[8 * i + 2 * e + 1] += bf_hi(c[e]) + bf_hi(b[e]);
          }
        }
        if (tid == 0) PROF_EV(14);
        wg_wait<0>();
        fence_regs<32, 32>(ct);
#pragma unroll
        for (int i = 0; i < 32; i++) sum[i] += ct[32 + i];
        const uint32_t stg = sb + OFF_T + warp * 2048;
        const int mr = (lane & 7) + ((lane >> 3) & 1) * 8, mc = lane >> 4;
#pragma unroll
        for (int i = 0; i < 4; i++) {
          const uint32_t a = stg + mr * 128 + (((2 * i + mc) ^ (mr & 7)) << 4);
          asm volatile("stmatrix.sync.aligned.m8n8.x4.shared.b16 [%0], {%1,%2,%3,%4};" ::"r"(a), "r"(pack_bf16(sum[8 * i], sum[8 * i + 1])),
                       "r"(pack_bf16(sum[8 * i + 2], sum[8 * i + 3])), "r"(pack_bf16(sum[8 * i + 4], sum[8 * i + 5])),
                       "r"(pack_bf16(sum[8 * i + 6], sum[8 * i + 7])) : "memory");
        }
        asm volatile("fence.proxy.async.shared::cta;" ::: "memory");
        __syncwarp();
        if (elect_one()) {
          asm volatile("cp.async.bulk.tensor.3d.global.shared::cta.bulk_group [%0, {%2, %3, %4}], [%1];" ::"l"(&maps.o), "r"(stg), "r"(64 * j),
                       "r"(16 * w), "r"(2 * rb + wg) : "memory");
          asm volatile("cp.async.bulk.commit_group;\ncp.async.bulk.wait_group.read 0;" ::: "memory");
        }
      }
      if (tid == 0) { PROF_EV(15); PROF_CK(41); }
      if (tid == 128) PROF_EV(30);
    }
  } else if (warp < 12) {
    asm volatile("setmaxnreg.dec.sync.aligned.u32 104;");
    asm volatile("barrier.cluster.arrive.relaxed.aligned;" ::: "memory");
    const int t = tid - 256, w = warp - 8;
    const uint32_t ep = ld_x1(&ws->epoch[blockIdx.x * 8]);
    const uint32_t tag = (ep + 1) & 1;
    auto w_issue = [&](const CUtensorMap* m) {

      if (elect_one()) { mbar_expect_tx(bars + 8 * (B_WR + w), 3072); tma4d(sb + OFF_T + w * 3072, m, bars + 8 * (B_WR + w), 16 * kg, 0, 2 * w, tn); }

          __syncwarp();
    };
    auto gate_rows = [&] {
      const int r = 16 * j + 4 * w + (lane >> 3);
      const uint4* pg = (const uint4*)gate_w + (lane & 7);
      {
        float a = 0.f;
        asm volatile("bar.sync 4, 256;" ::: "memory");
#pragma unroll 1
        for (int hf = 0; hf < 2; hf++) {
          uint4 v[4], u[4];
#pragma unroll
          for (int kb = 0; kb < 4; kb++) v[kb] = __ldg(pg + (4 * hf + kb) * 8);
          mbar_wait(bars + 8 * (B_FE + 1 + 2 * hf), 0);
          if (hf) w_issue(&maps.wr);
#pragma unroll
          for (int kb = 0; kb < 4; kb++) u[kb] = *(const uint4*)(smem + (4 * hf + kb) * U + r * 128 + (((lane ^ r) & 7) << 4));
#pragma unroll
          for (int kb = 0; kb < 4; kb++) {
            a = fmaf(bf_lo(u[kb].x), bf_lo(v[kb].x), a); a = fmaf(bf_hi(u[kb].x), bf_hi(v[kb].x), a);
            a = fmaf(bf_lo(u[kb].y), bf_lo(v[kb].y), a); a = fmaf(bf_hi(u[kb].y), bf_hi(v[kb].y), a);
            a = fmaf(bf_lo(u[kb].z), bf_lo(v[kb].z), a); a = fmaf(bf_hi(u[kb].z), bf_hi(v[kb].z), a);
            a = fmaf(bf_lo(u[kb].w), bf_lo(v[kb].w), a); a = fmaf(bf_hi(u[kb].w), bf_hi(v[kb].w), a);
          }
        }
#pragma unroll
        for (int o = 4; o; o >>= 1) a += __shfl_xor_sync(0xffffffffu, a, o);
        if ((lane & 7) == 0)
          asm volatile("st.relaxed.gpu.global.f32 [%0], %1;" ::"l"(ws->gate + rb * 128 + r), "f"(tagf(__fdividef(1.0f, 1.0f + __expf(-a)), tag)) : "memory");
        if (t == 0) PROF_EV(18);
      }
    };
    {
      const int g = lane >> 2, q = lane & 3;
      uint32_t wf[32];
      if (!helper) {
        gate_rows();
        const uint32_t wa = sb + OFF_T + w * (3072 + 4) + q * 48 + g * 2;
#pragma unroll 1
        for (int ri = 0; ri < 2; ri++) {
          mbar_wait(bars + 8 * (B_WR + w), ri);
#pragma unroll
          for (int n2 = 0; n2 < 32 / WB; n2++) {
            uint32_t v[WB];
#pragma unroll
            for (int i = 0; i < WB; i++) {
              const int e = n2 * WB + i;
              asm volatile("ld.shared.u16 %0, [%1];" : "=r"(v[i]) : "r"(wa + ((e >> 1) & 7) * 192 + (e & 1) * (1536 + 2) + (e >> 4) * 16) : "memory");
            }
#pragma unroll
            for (int i = 0; i < WB; i++) wf[n2 * WB + i] = __byte_perm(wf[n2 * WB + i], v[i], 0x5432);
            if (WSLEEP) { asm volatile("nanosleep.u32 %0;" ::"r"(WSLEEP + (v[WB - 1] >> 16)) : "memory"); }
          }
          __syncwarp();
          if (ri == 0) w_issue(&maps.wi);
        }
        asm volatile("bar.sync 1, 128;" ::: "memory");
        if (t == 0) PROF_EV(11);
      } else {
        asm volatile("bar.sync 4, 256;" ::: "memory");
        hint_wait(&ws->cntW[0], (ep + 1) * 128u);
        const uint32_t t0 = (uint32_t)clock();
#pragma unroll 1
        for (;;) {
          uint32_t bad = 0;
#pragma unroll
          for (int i = 0; i < 32; i++) {
            const float2 v = ld_x2((const float2*)ws->Wh + (i >> 4) * 2048 + 16 * w + g + 8 * (i & 1) + 64 * q + ((i >> 1) & 7) * 256);
            wf[i] = __float_as_uint(v.x); bad |= __float_as_uint(v.y) ^ tag;
          }
          if (!__any_sync(0xffffffffu, bad & 1)) break;
          spin_guard(t0);
        }
        if (t == 0) PROF_EV(11);
      }
      if (w == 0 && elect_one()) { mbar_expect_tx(bars + 8 * B_W, 8192); bulk_load(sb + OFF_D, dtab, 8192, bars + 8 * B_W); }
      asm volatile("barrier.cluster.wait.aligned;" ::: "memory");
      mbar_wait(bars + 8 * B_W, 0);
      mbar_wait(bars + 8 * B_HX, 0);
      if (t == 0) PROF_EV(12);
      const uint32_t dd = (sb & 0x3FFFF) >> 4;
      const uint64_t dF = d128((dd + (OFF_D >> 4)) | (512u << 16)), dI = d128((dd + (OFF_D >> 4)) | (1u << 16)), dA = d128((dd + (OFF_XB >> 4)) | (512u << 16));
      float az[32];
      const int zero = blockIdx.x >> 16;
      uint32_t pf[32];
#pragma unroll
      for (int mt = 0; mt < 2; mt++) {
        wg_fence();
        if (mt == 0) mma_ss64<0, 3, 0>(az, dA, dF);
        else mma_ss64<0, 3, 2>(az, dA + 512, dF, zero);
#pragma unroll
        for (int k = 1; k < 4; k++) mma_ss64<0, 3, 1>(az, dA + (mt * 512 + k * 128), dF + k * 128);
        wg_commit();
        wg_wait<0>();
        fence_regs<0, 32>(az);
#pragma unroll
        for (int i = 0; i < 16; i++) {
          const float wr = bf_lo(wf[16 * mt + i]), wi = bf_hi(wf[16 * mt + i]);
          pf[16 * mt + i] = pack_pin(fmaf(az[2 * i], wr, -az[2 * i + 1] * wi), fmaf(az[2 * i], wi, az[2 * i + 1] * wr));
        }
      }
      if (t == 0) PROF_EV(16);
      {
        const int m = lane >> 3, r = lane & 7;
        const int sl = 2 * (m >> 1) + ((r >> 1) & 1) + 4 * (r >> 2);
        const uint32_t a0 = sb + OFF_XB + (2 * w + (m & 1)) * 2048 + sl * 64;
        uint32_t pk[16];
#pragma unroll
        for (int mt = 0; mt < 3; mt++) {
          if (mt < 2) {
            wg_fence();
            mma_rs64<0, 0, 2>(az, pf[16 * mt], pf[16 * mt + 1], pf[16 * mt + 2], pf[16 * mt + 3], dI, mt ? (int)helper : zero);
#pragma unroll
            for (int k = 1; k < 4; k++) mma_rs64<0, 0, 1>(az, pf[16 * mt + 4 * k], pf[16 * mt + 4 * k + 1], pf[16 * mt + 4 * k + 2], pf[16 * mt + 4 * k + 3], dI + k * 2);
            wg_commit();
          }
          if (mt > 0 && !helper) {
#pragma unroll
            for (int i = 0; i < 4; i++) stsm4t(a0 + ((((mt - 1) * 2 + (r & 1)) ^ (sl >> 1)) << 4) + i * 512, pk[4 * i], pk[4 * i + 1], pk[4 * i + 2], pk[4 * i + 3]);
          }
          if (mt < 2) {
            wg_wait<0>();
            fence_regs<0, 32>(az);
#pragma unroll
            for (int i = 0; i < 16; i++) pk[i] = pack_pin(az[2 * i], az[2 * i + 1]);
          }
        }
      }
      if (helper) {
#pragma unroll
        for (int i = 0; i < 16; i++) {
          const int n = i >> 1, s0 = 8 * (n >> 1) + 2 * (n & 1) + (q & 1) + 4 * (q >> 1);
          if ((n & 1) == (int)(blockIdx.x & 1)) st_u2(ws->Ts + s0 * 64 + 16 * w + g + 8 * (i & 1), pack_bf16(az[2 * i], az[2 * i + 1]), tag);
        }
        __syncwarp();
        hint_add_if(lane == 0, &ws->cntH[0]);
        if (t == 0) { ws->epoch[blockIdx.x * 8] = ep + 1; PROF_EV(13); }
      } else {
        asm volatile("fence.proxy.async.shared::cta;" ::: "memory");
        __syncwarp();
        if (elect_one()) {
          if (t == 0) PROF_EV(17);
          if (SPACE) __nanosleep(SPACE * w);
          asm volatile("cp.async.bulk.tensor.3d.global.shared::cta.bulk_group [%0, {%2, %3, %4}], [%1];" ::"l"(&maps.ts), "r"(sb + OFF_XB + w * 4096),
                       "r"(32 * kg), "r"(0), "r"(8 * tn + 2 * w) : "memory");
          bulk_done_signal(&ws->cntT[32 * j]);
          asm volatile("mbarrier.arrive.shared::cluster.b64 _, [%0];" ::"r"(mapa(bars + 8 * B_RD0, rank ^ 1)) : "memory");
          if (t == 96) PROF_EV(13);
        }
        __syncwarp();
        if (j == 0) {
          hint_wait(&ws->cntH[0], (ep + 1) * 8u);
          const uint32_t t0 = (uint32_t)clock();
          float2 v;
          do { v = ld_x2((const float2*)ws->Ts + 2 * rb * 64 + t); spin_guard(t0); } while (__any_sync(0xffffffffu, (__float_as_uint(v.y) ^ tag) & 1));
          mbar_wait(bars + 8 * B_TL, 0);
          const uint32_t u = __float_as_uint(v.x);
          *(uint16_t*)(smem + OFF_T + t * 128 + ((t & 7) << 4)) = (uint16_t)u;
          *(uint16_t*)(smem + OFF_T + t * 128 + (((t & 7) ^ 1) << 4)) = (uint16_t)(u >> 16);
          asm volatile("fence.proxy.async.shared::cta;" ::: "memory");
          __syncwarp();
          mbar_arrive_if(lane == 0, bars + 8 * B_T);
        }
      }
    }
  } else {
    asm volatile("setmaxnreg.dec.sync.aligned.u32 24;");
    auto xf_load = [&](int q) {
      const uint32_t fb = bars + 8 * (B_FX + q);
      mbar_expect_tx(fb, U + 8192);
      tma3d(sb + q * U, &maps.x, fb, 64 * q, 0, 2 * rb);
      if (q >= 4) mbar_wait(bars + 8 * (B_FE + ((q - 4) >> 1)), 0);
      tma2d(sb + OFF_XB + (q & 3) * 8192, &maps.ft, fb, 64 * q, 64 * j);
    };
    if (elect_one()) {
      if (warp == 14) {
#pragma unroll
        for (int i = 0; i < B_FT; i++) mbar_init(bars + 8 * i, 1);
        asm volatile("fence.mbarrier_init.release.cluster;" ::: "memory");
        if (!helper) {
#pragma unroll 1
          for (int n = 0; n < 2; n++) {
            const uint32_t fb = bars + 8 * (B_FA + n);
            xf_load(2 * n); xf_load(2 * n + 1);
            mbar_expect_tx(fb, U);
            tma2d(sb + OFF_RING + n * U, &maps.g64, fb, f_full, 64 * n);
            tma2d(sb + OFF_RING + n * U + 8192, &maps.u64, fb, f_full, 64 * n);
          }
        }
      } else if (warp == 15) {
#pragma unroll
        for (int i = B_FT; i < NBAR; i++) mbar_init(bars + 8 * i, i < B_EA ? 1 : i < B_T ? 2 : 4);
#pragma unroll
        for (int i = 0; i < 8; i++) mbar_expect_tx(bars + 8 * (B_Z + i), U / 2);
        asm volatile("fence.mbarrier_init.release.cluster;" ::: "memory");
        asm volatile("fence.proxy.async.shared::cta;" ::: "memory");
      } else if (warp == 13 && !PF0) {
#pragma unroll
        for (int i = 1; i < 4; i++) asm volatile("prefetch.tensormap [%0];" ::"l"((const char*)&maps + i * 128) : "memory");
      }
    }
    __syncwarp();
    asm volatile("bar.arrive 0, 384;" ::: "memory");
    asm volatile("bar.arrive 4, 256;" ::: "memory");
    __syncwarp();
    asm volatile("barrier.cluster.arrive.relaxed.aligned;" ::: "memory");
    asm volatile("bar.sync 3, 128;" ::: "memory");
    if (warp == 15 && !helper) {
        mbar_wait(bars + 8 * B_FE, 0);
        const uint32_t tag = (ld_x1(&ws->epoch[blockIdx.x * 8]) + 1) & 1;
        const int c = lane >> 4, jj = 16 * blockIdx.x + (lane & 15), jm = (2048 - jj) & 2047;
        const unsigned short* pr = (const unsigned short*)w_r + 256 * c;
        const unsigned short* pi = (const unsigned short*)w_i + 256 * c;
        const float wr = 0.25f * (bf_lo(__ldg(pr + jj * 257)) + bf_lo(__ldg(pr + jm * 257)));
        const float wi = 0.25f * (bf_lo(__ldg(pi + jj * 257)) - bf_lo(__ldg(pi + jm * 257)));
        st_u2(ws->Wh + c * 2048 + jj, c ? pack_bf16(-wi, wr) : pack_bf16(wr, wi), tag);
        __syncwarp();
        hint_add_if(lane == 0, &ws->cntW[0]);
        mbar_wait(bars + 8 * B_XS, 0);
        const uint32_t t0 = (uint32_t)clock();
        uint4 v;
        do { v = ld_x4(ws->gate + rb * 128 + 4 * lane); spin_guard(t0); } while (__any_sync(0xffffffffu, ((v.x ^ tag) | (v.y ^ tag) | (v.z ^ tag) | (v.w ^ tag)) & 1));
        *(uint4*)(smem + OFF_G + lane * 16) = v;
        __syncwarp();
        mbar_arrive_if(lane < 4, bars + 8 * B_G);
      }
    if ((!helper || warp == 15) && elect_one()) {
      if (warp < 14) {
        const int p = warp - 12;
#pragma unroll 1
        for (int i = 4 + p; i < 14; i += 2) asm volatile("prefetch.tensormap [%0];" ::"l"((const char*)&maps + i * 128) : "memory");
#pragma unroll 1
        for (int n = 2; n < 31; n++) {
          const bool table = n == 4 || n >= 29;
          const bool half = n >= 17 && n < 21;
          const int q = n < 4 ? n : n < 17 ? n - 1 : n - 5;
          const CUtensorMap* m = table ? &maps.e : half ? &maps.g32 + p : &maps.g64 + p;
          const int c0 = table ? 0 : half ? f_half : f_full + 64 * (q >> 3);
          const int c1 = table ? (2 * rb + ((n & 1) ^ 1)) * 128 + 64 * p : half ? 128 * (n - 17) : 64 * (q & 7);
          const uint32_t fb = bars + 8 * (B_FA + (n & 3)), dst = sb + OFF_RING + (n & 3) * U + p * 8192;
          if (n < 4) mbar_wait(bars + 8 * (B_FE + n - 2), 0);
          else mbar_wait(bars + 8 * (B_EA + (n & 3)), ((n >> 2) & 1) ^ 1);
          tma2d(dst, m, fb, c0, c1);
          if (p == 0) mbar_expect_tx(fb, U);
        }
      } else if (warp == 15) {
        const unsigned ep1 = ld_x1(&ws->epoch[blockIdx.x * 8]) + 1;
        flag_wait(&ws->cntX[helper ? 0 : 32 * j], ep1 * 16u);
        PROF_EV(22);
        mbar_expect_tx(bars + 8 * B_HX, U);
        bulk_load(sb + OFF_XB, ws->X + (size_t)(helper ? 128 : kg * 8 + tn) * 8192, U, bars + 8 * B_HX);
        if (!helper) {
          flag_wait(&ws->cntT[32 * j], ep1 * 64u);
          PROF_EV(23);
          mbar_expect_tx(bars + 8 * B_TL, U);
          tma3d(sb + OFF_T, &maps.t, bars + 8 * B_TL, 64 * j, 0, 2 * rb);
#pragma unroll 1
          for (int i = 0; i < 3; i++) {
            flag_wait(&ws->cntP[32 * (rb * 8 + j) + i], ep1 * 8u);
            mbar_wait(bars + 8 * (B_PZ + (i == 0)), 0);
            if (i == 2) PROF_EV(26);
            mbar_expect_tx(bars + 8 * (B_HP + i), U);
            bulk_load(sb + (i ? (i - 1) * U : OFF_T), ws->part + (size_t)((rb * 8 + j) * 3 + i) * 1024, U, bars + 8 * (B_HP + i));
          }
          ws->epoch[blockIdx.x * 8] = ep1;
        }
      } else {
#pragma unroll 1
        for (int q = 4; q < 8; q++) xf_load(q);
        mbar_wait(bars + 8 * (B_FE + 2), 0);
        mbar_expect_tx(bars + 8 * B_E0, U);
        tma2d(sb + OFF_XB, &maps.e, bars + 8 * B_E0, 0, 2 * rb * 128);
        tma2d(sb + OFF_XB + 8192, &maps.e, bars + 8 * B_E0, 0, 2 * rb * 128 + 64);
#pragma unroll 1
        for (int h2 = 0; h2 < 2; h2++) {
          const int s0 = 2 * rb + h2, sg = (s0 & ~6) | ((s0 & 2) << 1) | ((s0 & 4) >> 1);
          mbar_wait(bars + 8 * (B_XS + h2), 0);
#pragma unroll 1
          for (int c = 0; c < 2; c++) {
            asm volatile("cp.async.bulk.tensor.4d.global.shared::cta.bulk_group [%0, {%2, %3, %4, %5}], [%1];" ::"l"(&maps.xs),
                         "r"(sb + OFF_XB + h2 * 8192 + c * 4096), "r"(0), "r"(sg), "r"(0), "r"(16 * j + 8 * c) : "memory");
            if (j == 0)
              asm volatile("cp.async.bulk.global.shared::cta.bulk_group [%0], [%1], 256;" ::"l"(ws->X + 128 * 8192 + c * 4096 + sg * 128),
                           "r"(sb + OFF_SP + h2 * 512 + c * 256) : "memory");
            if (SPACE && h2 + c < 2) __nanosleep(SPACE);
          }
        }
        bulk_done_signal(&ws->cntX[32 * j]);
        PROF_EV(20);
        if (rb < 8) asm volatile("cp.async.bulk.prefetch.tensor.2d.L2.global [%0, {%1, %2}];" ::"l"(&maps.g32 + (rb >> 2)), "r"(f_half), "r"(128 * (rb & 3)) : "memory");
        else asm volatile("cp.async.bulk.prefetch.tensor.2d.L2.global [%0, {%1, %2}];" ::"l"(&maps.d224), "r"(64 * (rb - 8)), "r"(224 * j) : "memory");
#pragma unroll 1
        for (int t = 0; t < 8; t++) {
          const int i = t < 3 ? t + 1 : t < 6 ? t - 2 : 0;
          const int col = 64 * (2 * ((q4 + i) & 3) + ((t < 3 || t == 6) ? 1 - rank : rank));
          const uint32_t fb = bars + 8 * (B_FT + (t & 3)), dst = sb + (t & 3) * TB;
          mbar_wait(bars + 8 * (B_ET + (t == 2 ? 3 : t & 3)), t >> 2);
          mbar_expect_tx(fb, TB);
          tma2d(dst, &maps.d224, fb, col, 224 * j);
          if (t < 2) mbar_wait(bars + 8 * (B_ET + t + 1), 0);
          tma2d(dst + 28672, &maps.ft, fb, col, 64 * j);
        }
      }
    }
  }
}

typedef CUresult (*EncodeFn)(CUtensorMap*, CUtensorMapDataType, cuuint32_t, void*, const cuuint64_t*, const cuuint64_t*, const cuuint32_t*,
                             const cuuint32_t*, CUtensorMapInterleave, CUtensorMapSwizzle, CUtensorMapL2promotion, CUtensorMapFloatOOBfill);

static void encode(EncodeFn f, CUtensorMap* m, const void* base, int rank, const cuuint64_t* dims, const cuuint64_t* strides, const cuuint32_t* box,
                   CUtensorMapSwizzle sw) {
  cuuint32_t es[5] = {1, 1, 1, 1, 1};
  f(m, CU_TENSOR_MAP_DATA_TYPE_BFLOAT16, rank, (void*)base, dims, strides, box, es, CU_TENSOR_MAP_INTERLEAVE_NONE, sw,
    CU_TENSOR_MAP_L2_PROMOTION_L2_128B, CU_TENSOR_MAP_FLOAT_OOB_FILL_NONE);
}

extern "C" void kernel_launch(void* const* d_in, const int* in_sizes, int n_in, void* d_out, int out_size) {
  (void)in_sizes; (void)n_in; (void)out_size;
  const __nv_bfloat16* x = (const __nv_bfloat16*)d_in[0];
  const __nv_bfloat16* w_r = (const __nv_bfloat16*)d_in[1];
  const __nv_bfloat16* w_i = (const __nv_bfloat16*)d_in[2];
  const __nv_bfloat16* Wg = (const __nv_bfloat16*)d_in[4];
  const __nv_bfloat16* Wu = (const __nv_bfloat16*)d_in[5];
  const __nv_bfloat16* Wd = (const __nv_bfloat16*)d_in[6];
  const __nv_bfloat16* gw = (const __nv_bfloat16*)d_in[7];

  void* fp = nullptr; cudaDriverEntryPointQueryResult qr;
  cudaGetDriverEntryPoint("cuTensorMapEncodeTiled", &fp, cudaEnableDefault, &qr);
  EncodeFn enc = (EncodeFn)fp;
  void *pFT, *pET, *pDT, *pW;
  cudaGetSymbolAddress(&pDT, g_DT); cudaGetSymbolAddress(&pW, g_work);
  void *pX = ((Work*)pW)->X, *pT = ((Work*)pW)->T;
  cudaGetSymbolAddress(&pFT, g_FT); cudaGetSymbolAddress(&pET, g_ET);

  Maps mp;
  const CUtensorMapSwizzle S128 = CU_TENSOR_MAP_SWIZZLE_128B, S64 = CU_TENSOR_MAP_SWIZZLE_64B;
  { cuuint64_t d[3] = {512, 64, 32}, s[2] = {32768, 1024}; cuuint32_t b[3] = {64, 64, 2}, b2[3] = {64, 16, 1};
    encode(enc, &mp.x, x, 3, d, s, b, S128); encode(enc, &mp.o, d_out, 3, d, s, b2, S128); }
  { cuuint64_t d[2] = {512, 512}, s[1] = {1024}; cuuint32_t b[2] = {64, 64}; encode(enc, &mp.ft, pFT, 2, d, s, b, S128); }
  { cuuint64_t d[4] = {128, 32, 2, 129}, s[3] = {256, 8192, 16384}; cuuint32_t b[4] = {128, 1, 2, 8}; encode(enc, &mp.xs, pX, 4, d, s, b, CU_TENSOR_MAP_SWIZZLE_NONE); }
  { cuuint64_t d[3] = {512, 32, 64}, s[2] = {65536, 1024}; cuuint32_t b[3] = {32, 32, 2}; encode(enc, &mp.ts, pT, 3, d, s, b, S64); }
  { cuuint64_t d[3] = {512, 64, 32}, s[2] = {1024, 65536}; cuuint32_t b[3] = {64, 64, 2}; encode(enc, &mp.t, pT, 3, d, s, b, S128); }
  { cuuint64_t d[2] = {64, 4096}, s[1] = {128}; cuuint32_t b[2] = {64, 64}; encode(enc, &mp.e, pET, 2, d, s, b, S128); }
  { cuuint64_t d[2] = {1792, 512}, s[1] = {3584}; cuuint32_t b[2] = {64, 64}, b2[2] = {32, 128};
    encode(enc, &mp.g64, Wg, 2, d, s, b, S128); encode(enc, &mp.u64, Wu, 2, d, s, b, S128);
    encode(enc, &mp.g32, Wg, 2, d, s, b2, S64); encode(enc, &mp.u32, Wu, 2, d, s, b2, S64); }
  { cuuint64_t d[2] = {512, 1792}, s[1] = {1024}; cuuint32_t b[2] = {64, 224}; encode(enc, &mp.d224, Wd, 2, d, s, b, S128); }
  { cuuint64_t d[4] = {264, 32, 8, 8}, s[3] = {32896, 512, 4112}; cuuint32_t b[4] = {24, 32, 2, 1};
    encode(enc, &mp.wr, w_r, 4, d, s, b, CU_TENSOR_MAP_SWIZZLE_NONE); encode(enc, &mp.wi, w_i, 4, d, s, b, CU_TENSOR_MAP_SWIZZLE_NONE); }

  cudaFuncSetAttribute(fused_kernel, cudaFuncAttributeMaxDynamicSharedMemorySize, SMEM_BYTES);
  fused_kernel<<<NCTA, 512, SMEM_BYTES>>>((Work*)pW, (const uint16_t*)pDT, w_r, w_i, gw, x, (const uint16_t*)pFT, Wg, Wu, mp);
}
```

```cpp
#include <cuda_runtime.h>
#include <cuda_bf16.h>
#include <cuda.h>
#include <stdint.h>

namespace tbl {
constexpr double PI = 3.14159265358979323846264338327950288;
constexpr double sin_s(double x) { double t = x, s = x; for (int n = 1; n < 12; n++) { t *= -x * x / ((2 * n) * (2 * n + 1)); s += t; } return s; }
constexpr double cos_s(double x) { double t = 1, s = 1; for (int n = 1; n < 12; n++) { t *= -x * x / ((2 * n - 1) * (2 * n)); s += t; } return s; }
constexpr double cos2048(int m) {
  m &= 2047; if (m > 1024) m = 2048 - m;
  bool neg = false; if (m > 512) { m = 1024 - m; neg = true; }
  double v = (m <= 256) ? cos_s(2 * PI * m / 2048) : sin_s(2 * PI * (512 - m) / 2048);
  return neg ? -v : v;
}
constexpr uint16_t to_bf16(double v) {
  if (v == 0) return 0;
  uint16_t s = 0; if (v < 0) { s = 0x8000; v = -v; }
  int e = 0; while (v >= 2) { v /= 2; e++; } while (v < 1) { v *= 2; e--; }
  double m = (v - 1) * 128; int mi = (int)m; double fr = m - mi;
  if (fr > 0.5 || (fr == 0.5 && (mi & 1))) mi++;
  if (mi == 128) { mi = 0; e++; }
  return (uint16_t)(s | ((e + 127) << 7) | mi);
}
struct CosT { uint16_t v[2048]; constexpr CosT() : v() { for (int i = 0; i < 2048; i++) v[i] = to_bf16(cos2048(i)); } };
struct alignas(1024) FT {
  uint16_t v[512 * 512];
  constexpr FT() : v() {
    CosT c;
    for (int r = 0; r < 512; r++) {
      int k = (r >> 4) * 8 + (r & 7), e = (r >> 3) & 1;
      int mul = 4 * k, add = e ? 512 : 0;
      if (k == 0 && e == 1) { mul = 1024; add = 0; }
      for (int d = 0; d < 512; d++) v[r * 512 + d] = c.v[(d * mul + add) & 2047];
    }
  }
};
struct alignas(1024) ET {
  uint16_t v[2048 * 128];
  constexpr ET() : v() {
    CosT c;
    for (int s = 0; s < 2048; s++)
      for (int j = 0; j < 64; j++) {
        const int o = (s & 31) * 8192 + (s >> 5) * 64 + j;
        v[o] = c.v[(s * j) & 2047]; v[o + 4096] = c.v[(s * j + 512) & 2047];
      }
  }
};
struct alignas(1024) DT {
  uint16_t v[64 * 64];
  constexpr DT() : v() {
    CosT c;
    for (int r = 0; r < 64; r++)
      for (int n = 0; n < 64; n++) {
        const int sg = r >> 1, s0 = (sg & ~6) | ((sg & 2) << 1) | ((sg & 4) >> 1), e = r & 1, f = n & 1;
        const int m = 64 * s0 * (n >> 1) + (e == f ? 0 : e ? -512 : 512);
        v[r * 64 + (((n >> 3) ^ (r & 7)) << 3) + (n & 7)] = c.v[m & 2047];
      }
  }
};
}

__device__ constexpr tbl::FT g_FT = tbl::FT();
__device__ constexpr tbl::ET g_ET = tbl::ET();
__device__ constexpr tbl::DT g_DT = tbl::DT();

struct alignas(1024) Work {
  unsigned epoch[132 * 8];
  unsigned cntX[8 * 32], cntT[8 * 32], cntP[128 * 32], cntW[32], cntH[32];
  alignas(16) float gate[16 * 128];
  alignas(16) uint2 Wh[2 * 2048];
  alignas(16) uint2 Ts[32 * 64];
  alignas(1024) uint16_t X[129 * 8192];
  alignas(1024) uint16_t T[32 * 64 * 512];
  alignas(1024) uint4 part[128 * 3 * 1024];
};
__device__ Work g_work;
#define PROF_EV(i) do {} while (0)
#define PROF_CK(i) do {} while (0)

__device__ __forceinline__ uint32_t smem_u32(const void* p) { return (uint32_t)__cvta_generic_to_shared(p); }
__device__ __forceinline__ void mbar_init(uint32_t bar, uint32_t cnt) { asm volatile("mbarrier.init.shared::cta.b64 [%0], %1;" ::"r"(bar), "r"(cnt)); }
__device__ __forceinline__ void mbar_expect_tx(uint32_t bar, uint32_t bytes) { asm volatile("mbarrier.arrive.expect_tx.shared::cta.b64 _, [%0], %1;" ::"r"(bar), "r"(bytes) : "memory"); }
__device__ __forceinline__ void mbar_arrive(uint32_t bar) { asm volatile("mbarrier.arrive.shared::cta.b64 _, [%0];" ::"r"(bar) : "memory"); }
__device__ __forceinline__ bool elect_one() {
  uint32_t p;
  asm volatile("{\n.reg .pred p;\nelect.sync _|p, 0xffffffff;\nselp.u32 %0, 1, 0, p;\n}" : "=r"(p));
  return p;
}
__device__ __forceinline__ void mbar_arrive_if(bool p, uint32_t bar) {
  asm volatile("{\n.reg .pred p;\nsetp.ne.b32 p, %1, 0;\n@p mbarrier.arrive.shared::cta.b64 _, [%0];\n}" ::"r"(bar), "r"((int)p) : "memory");
}
__device__ __forceinline__ void hint_add_if(bool p, unsigned* a) {
  asm volatile("{\n.reg .pred p;\nsetp.ne.b32 p, %1, 0;\n@p red.relaxed.gpu.global.add.u32 [%0], 1;\n}" ::"l"(a), "r"((int)p) : "memory");
}
__device__ __forceinline__ bool mbar_try(uint32_t bar, uint32_t parity) {
  uint32_t ok;
  asm volatile("{\n.reg .pred p;\nmbarrier.test_wait.parity.shared::cta.b64 p, [%1], %2;\nselp.u32 %0, 1, 0, p;\n}" : "=r"(ok) : "r"(bar), "r"(parity) : "memory");
  return ok;
}
__device__ __forceinline__ void mbar_wait(uint32_t bar, uint32_t parity) {
  asm volatile(
      "{\n.reg .pred p;\n.reg .u32 n;\nmov.u32 n, 0;\n"
      "W_LOOP:\nmbarrier.try_wait.parity.shared::cta.b64 p, [%0], %1;\n@p bra W_DONE;\n"
      "add.u32 n, n, 1;\nsetp.lt.u32 p, n, 0x40000;\n@p bra W_LOOP;\ntrap;\nW_DONE:\n}" ::"r"(bar), "r"(parity) : "memory");
}
__device__ __forceinline__ void bulk_load(uint32_t dst, const void* src, uint32_t bytes, uint32_t bar) {
  asm volatile("cp.async.bulk.shared::cluster.global.mbarrier::complete_tx::bytes [%0], [%1], %2, [%3];" ::"r"(dst), "l"(src), "r"(bytes), "r"(bar) : "memory");
}
__device__ __forceinline__ void spin_guard(uint32_t t0) { if ((uint32_t)clock() - t0 > (1u << 30)) __trap(); }
__device__ __forceinline__ float2 ld_x2(const float2* p) { float2 v; asm volatile("ld.relaxed.gpu.global.v2.f32 {%0,%1}, [%2];" : "=f"(v.x), "=f"(v.y) : "l"(p) : "memory"); return v; }
__device__ __forceinline__ void st_u2(uint2* p, uint32_t a, uint32_t b) { asm volatile("st.relaxed.gpu.global.v2.u32 [%0], {%1,%2};" ::"l"(p), "r"(a), "r"(b) : "memory"); }
__device__ __forceinline__ uint32_t ld_x1(const void* p) { uint32_t v; asm volatile("ld.relaxed.gpu.global.u32 %0, [%1];" : "=r"(v) : "l"(p) : "memory"); return v; }
__device__ __forceinline__ uint4 ld_x4(const void* p) { uint4 v; asm volatile("ld.relaxed.gpu.global.v4.u32 {%0,%1,%2,%3}, [%4];" : "=r"(v.x), "=r"(v.y), "=r"(v.z), "=r"(v.w) : "l"(p) : "memory"); return v; }
__device__ __forceinline__ uint32_t mapa(uint32_t a, uint32_t cta) { uint32_t r; asm volatile("mapa.shared::cluster.u32 %0, %1, %2;" : "=r"(r) : "r"(a), "r"(cta)); return r; }
__device__ __forceinline__ void stsm4t(uint32_t a, uint32_t r0, uint32_t r1, uint32_t r2, uint32_t r3) {
  asm volatile("stmatrix.sync.aligned.m8n8.x4.trans.shared.b16 [%0], {%1,%2,%3,%4};" ::"r"(a), "r"(r0), "r"(r1), "r"(r2), "r"(r3) : "memory");
}
__device__ __forceinline__ void hint_add(unsigned* p) { asm volatile("red.relaxed.gpu.global.add.u32 [%0], 1;" ::"l"(p) : "memory"); }
__device__ __forceinline__ void hint_wait(const unsigned* p, unsigned target) {
  const uint32_t t0 = (uint32_t)clock();
  while ((int)(ld_x1(p) - target) < 0) spin_guard(t0);
}
__device__ __forceinline__ void bulk_done_signal(unsigned* p) {
  asm volatile("cp.async.bulk.commit_group;\ncp.async.bulk.wait_group 0;\nfence.proxy.async.global;" ::: "memory");
  hint_add(p);
}
__device__ __forceinline__ void flag_wait(const unsigned* p, unsigned target) {
  hint_wait(p, target);
  asm volatile("fence.proxy.async.global;" ::: "memory");
}
__device__ __forceinline__ void tma2d(uint32_t dst, const CUtensorMap* m, uint32_t bar, int c0, int c1) {
  asm volatile("cp.async.bulk.tensor.2d.shared::cluster.global.mbarrier::complete_tx::bytes [%0], [%1, {%3, %4}], [%2];" ::"r"(dst), "l"(m), "r"(bar), "r"(c0), "r"(c1) : "memory");
}
__device__ __forceinline__ void tma3d(uint32_t dst, const CUtensorMap* m, uint32_t bar, int c0, int c1, int c2) {
  asm volatile("cp.async.bulk.tensor.3d.shared::cluster.global.mbarrier::complete_tx::bytes [%0], [%1, {%3, %4, %5}], [%2];" ::"r"(dst), "l"(m), "r"(bar), "r"(c0), "r"(c1), "r"(c2) : "memory");
}
__device__ __forceinline__ void tma4d(uint32_t dst, const CUtensorMap* m, uint32_t bar, int c0, int c1, int c2, int c3) {
  asm volatile("cp.async.bulk.tensor.4d.shared::cluster.global.mbarrier::complete_tx::bytes [%0], [%1, {%3, %4, %5, %6}], [%2];" ::"r"(dst), "l"(m), "r"(bar), "r"(c0), "r"(c1), "r"(c2), "r"(c3) : "memory");
}
__device__ __forceinline__ void wg_fence() { asm volatile("wgmma.fence.sync.aligned;" ::: "memory"); }
__device__ __forceinline__ void wg_commit() { asm volatile("wgmma.commit_group.sync.aligned;" ::: "memory"); }
template <int N> __device__ __forceinline__ void wg_wait() { asm volatile("wgmma.wait_group.sync.aligned %0;" ::"n"(N) : "memory"); }
template <int O, int N, int NN> __device__ __forceinline__ void fence_regs(float (&d)[NN]) {
#pragma unroll
  for (int i = 0; i < N; i++) asm volatile("" : "+f"(d[O + i])::"memory");
}
__device__ __forceinline__ uint32_t pack_bf16(float lo, float hi) {
  uint32_t r; asm("cvt.rn.bf16x2.f32 %0, %1, %2;" : "=r"(r) : "f"(hi), "f"(lo)); return r;
}
__device__ __forceinline__ uint32_t pack_pin(float lo, float hi) {
  uint32_t r; asm volatile("cvt.rn.bf16x2.f32 %0, %1, %2;" : "=r"(r) : "f"(hi), "f"(lo) : "memory"); return r;
}
__device__ __forceinline__ float bf_lo(uint32_t u) { return __uint_as_float(u << 16); }
__device__ __forceinline__ float bf_hi(uint32_t u) { return __uint_as_float(u & 0xffff0000u); }

__device__ __forceinline__ uint64_t d128(uint32_t lo) { uint64_t d; asm("mov.b64 %0, {%1, 0x40000040};" : "=l"(d) : "r"(lo)); return d; }
__device__ __forceinline__ uint64_t d64(uint32_t lo) { uint64_t d; asm("mov.b64 %0, {%1, 0x80000020};" : "=l"(d) : "r"(lo)); return d; }
template<int O,int TB,int ACC,int NN> __device__ __forceinline__ void mma_ss64(float (&d)[NN], uint64_t da, uint64_t db, int sd = 0){
  if constexpr (ACC == 1) asm volatile("wgmma.mma_async.sync.aligned.m64n64k16.f32.bf16.bf16 {%0,%1,%2,%3,%4,%5,%6,%7,%8,%9,%10,%11,%12,%13,%14,%15,%16,%17,%18,%19,%20,%21,%22,%23,%24,%25,%26,%27,%28,%29,%30,%31}, %32, %33, 1, 1, 1, %35, %34;"
   : "+f"(d[O+0]), "+f"(d[O+1]), "+f"(d[O+2]), "+f"(d[O+3]), "+f"(d[O+4]), "+f"(d[O+5]), "+f"(d[O+6]), "+f"(d[O+7]), "+f"(d[O+8]), "+f"(d[O+9]), "+f"(d[O+10]), "+f"(d[O+11]), "+f"(d[O+12]), "+f"(d[O+13]), "+f"(d[O+14]), "+f"(d[O+15]), "+f"(d[O+16]), "+f"(d[O+17]), "+f"(d[O+18]), "+f"(d[O+19]), "+f"(d[O+20]), "+f"(d[O+21]), "+f"(d[O+22]), "+f"(d[O+23]), "+f"(d[O+24]), "+f"(d[O+25]), "+f"(d[O+26]), "+f"(d[O+27]), "+f"(d[O+28]), "+f"(d[O+29]), "+f"(d[O+30]), "+f"(d[O+31])
   : "l"(da), "l"(db), "n"(TB & 1), "n"(TB >> 1));
  else if constexpr (ACC == 0) asm volatile("wgmma.mma_async.sync.aligned.m64n64k16.f32.bf16.bf16 {%0,%1,%2,%3,%4,%5,%6,%7,%8,%9,%10,%11,%12,%13,%14,%15,%16,%17,%18,%19,%20,%21,%22,%23,%24,%25,%26,%27,%28,%29,%30,%31}, %32, %33, 0, 1, 1, %35, %34;"
   : "=f"(d[O+0]), "=f"(d[O+1]), "=f"(d[O+2]), "=f"(d[O+3]), "=f"(d[O+4]), "=f"(d[O+5]), "=f"(d[O+6]), "=f"(d[O+7]), "=f"(d[O+8]), "=f"(d[O+9]), "=f"(d[O+10]), "=f"(d[O+11]), "=f"(d[O+12]), "=f"(d[O+13]), "=f"(d[O+14]), "=f"(d[O+15]), "=f"(d[O+16]), "=f"(d[O+17]), "=f"(d[O+18]), "=f"(d[O+19]), "=f"(d[O+20]), "=f"(d[O+21]), "=f"(d[O+22]), "=f"(d[O+23]), "=f"(d[O+24]), "=f"(d[O+25]), "=f"(d[O+26]), "=f"(d[O+27]), "=f"(d[O+28]), "=f"(d[O+29]), "=f"(d[O+30]), "=f"(d[O+31])
   : "l"(da), "l"(db), "n"(TB & 1), "n"(TB >> 1));
  else asm volatile("{\n.reg .pred p;\nsetp.ne.b32 p, %36, 0;\nwgmma.mma_async.sync.aligned.m64n64k16.f32.bf16.bf16 {%0,%1,%2,%3,%4,%5,%6,%7,%8,%9,%10,%11,%12,%13,%14,%15,%16,%17,%18,%19,%20,%21,%22,%23,%24,%25,%26,%27,%28,%29,%30,%31}, %32, %33, p, 1, 1, %35, %34;\n}"
   : "+f"(d[O+0]), "+f"(d[O+1]), "+f"(d[O+2]), "+f"(d[O+3]), "+f"(d[O+4]), "+f"(d[O+5]), "+f"(d[O+6]), "+f"(d[O+7]), "+f"(d[O+8]), "+f"(d[O+9]), "+f"(d[O+10]), "+f"(d[O+11]), "+f"(d[O+12]), "+f"(d[O+13]), "+f"(d[O+14]), "+f"(d[O+15]), "+f"(d[O+16]), "+f"(d[O+17]), "+f"(d[O+18]), "+f"(d[O+19]), "+f"(d[O+20]), "+f"(d[O+21]), "+f"(d[O+22]), "+f"(d[O+23]), "+f"(d[O+24]), "+f"(d[O+25]), "+f"(d[O+26]), "+f"(d[O+27]), "+f"(d[O+28]), "+f"(d[O+29]), "+f"(d[O+30]), "+f"(d[O+31])
   : "l"(da), "l"(db), "n"(TB & 1), "n"(TB >> 1), "r"(sd));
}
template<int O,int TB,int ACC,int NN> __device__ __forceinline__ void mma_rs64(float (&d)[NN], uint32_t a0, uint32_t a1, uint32_t a2, uint32_t a3, uint64_t db, int sd = 0){
  if constexpr (ACC == 1) asm volatile("wgmma.mma_async.sync.aligned.m64n64k16.f32.bf16.bf16 {%0,%1,%2,%3,%4,%5,%6,%7,%8,%9,%10,%11,%12,%13,%14,%15,%16,%17,%18,%19,%20,%21,%22,%23,%24,%25,%26,%27,%28,%29,%30,%31}, {%32,%33,%34,%35}, %36, 1, 1, 1, %37;"
   : "+f"(d[O+0]), "+f"(d[O+1]), "+f"(d[O+2]), "+f"(d[O+3]), "+f"(d[O+4]), "+f"(d[O+5]), "+f"(d[O+6]), "+f"(d[O+7]), "+f"(d[O+8]), "+f"(d[O+9]), "+f"(d[O+10]), "+f"(d[O+11]), "+f"(d[O+12]), "+f"(d[O+13]), "+f"(d[O+14]), "+f"(d[O+15]), "+f"(d[O+16]), "+f"(d[O+17]), "+f"(d[O+18]), "+f"(d[O+19]), "+f"(d[O+20]), "+f"(d[O+21]), "+f"(d[O+22]), "+f"(d[O+23]), "+f"(d[O+24]), "+f"(d[O+25]), "+f"(d[O+26]), "+f"(d[O+27]), "+f"(d[O+28]), "+f"(d[O+29]), "+f"(d[O+30]), "+f"(d[O+31])
   : "r"(a0), "r"(a1), "r"(a2), "r"(a3), "l"(db), "n"(TB));
  else if constexpr (ACC == 0) asm volatile("wgmma.mma_async.sync.aligned.m64n64k16.f32.bf16.bf16 {%0,%1,%2,%3,%4,%5,%6,%7,%8,%9,%10,%11,%12,%13,%14,%15,%16,%17,%18,%19,%20,%21,%22,%23,%24,%25,%26,%27,%28,%29,%30,%31}, {%32,%33,%34,%35}, %36, 0, 1, 1, %37;"
   : "=f"(d[O+0]), "=f"(d[O+1]), "=f"(d[O+2]), "=f"(d[O+3]), "=f"(d[O+4]), "=f"(d[O+5]), "=f"(d[O+6]), "=f"(d[O+7]), "=f"(d[O+8]), "=f"(d[O+9]), "=f"(d[O+10]), "=f"(d[O+11]), "=f"(d[O+12]), "=f"(d[O+13]), "=f"(d[O+14]), "=f"(d[O+15]), "=f"(d[O+16]), "=f"(d[O+17]), "=f"(d[O+18]), "=f"(d[O+19]), "=f"(d[O+20]), "=f"(d[O+21]), "=f"(d[O+22]), "=f"(d[O+23]), "=f"(d[O+24]), "=f"(d[O+25]), "=f"(d[O+26]), "=f"(d[O+27]), "=f"(d[O+28]), "=f"(d[O+29]), "=f"(d[O+30]), "=f"(d[O+31])
   : "r"(a0), "r"(a1), "r"(a2), "r"(a3), "l"(db), "n"(TB));
  else asm volatile("{\n.reg .pred p;\nsetp.ne.b32 p, %38, 0;\nwgmma.mma_async.sync.aligned.m64n64k16.f32.bf16.bf16 {%0,%1,%2,%3,%4,%5,%6,%7,%8,%9,%10,%11,%12,%13,%14,%15,%16,%17,%18,%19,%20,%21,%22,%23,%24,%25,%26,%27,%28,%29,%30,%31}, {%32,%33,%34,%35}, %36, p, 1, 1, %37;\n}"
   : "+f"(d[O+0]), "+f"(d[O+1]), "+f"(d[O+2]), "+f"(d[O+3]), "+f"(d[O+4]), "+f"(d[O+5]), "+f"(d[O+6]), "+f"(d[O+7]), "+f"(d[O+8]), "+f"(d[O+9]), "+f"(d[O+10]), "+f"(d[O+11]), "+f"(d[O+12]), "+f"(d[O+13]), "+f"(d[O+14]), "+f"(d[O+15]), "+f"(d[O+16]), "+f"(d[O+17]), "+f"(d[O+18]), "+f"(d[O+19]), "+f"(d[O+20]), "+f"(d[O+21]), "+f"(d[O+22]), "+f"(d[O+23]), "+f"(d[O+24]), "+f"(d[O+25]), "+f"(d[O+26]), "+f"(d[O+27]), "+f"(d[O+28]), "+f"(d[O+29]), "+f"(d[O+30]), "+f"(d[O+31])
   : "r"(a0), "r"(a1), "r"(a2), "r"(a3), "l"(db), "n"(TB), "r"(sd));
}
template<int O,int TB,int ACC,int NN> __device__ __forceinline__ void mma_ss128(float (&d)[NN], uint64_t da, uint64_t db, int sd = 0){
  if constexpr (ACC == 1) asm volatile("wgmma.mma_async.sync.aligned.m64n128k16.f32.bf16.bf16 {%0,%1,%2,%3,%4,%5,%6,%7,%8,%9,%10,%11,%12,%13,%14,%15,%16,%17,%18,%19,%20,%21,%22,%23,%24,%25,%26,%27,%28,%29,%30,%31,%32,%33,%34,%35,%36,%37,%38,%39,%40,%41,%42,%43,%44,%45,%46,%47,%48,%49,%50,%51,%52,%53,%54,%55,%56,%57,%58,%59,%60,%61,%62,%63}, %64, %65, 1, 1, 1, %67, %66;"
   : "+f"(d[O+0]), "+f"(d[O+1]), "+f"(d[O+2]), "+f"(d[O+3]), "+f"(d[O+4]), "+f"(d[O+5]), "+f"(d[O+6]), "+f"(d[O+7]), "+f"(d[O+8]), "+f"(d[O+9]), "+f"(d[O+10]), "+f"(d[O+11]), "+f"(d[O+12]), "+f"(d[O+13]), "+f"(d[O+14]), "+f"(d[O+15]), "+f"(d[O+16]), "+f"(d[O+17]), "+f"(d[O+18]), "+f"(d[O+19]), "+f"(d[O+20]), "+f"(d[O+21]), "+f"(d[O+22]), "+f"(d[O+23]), "+f"(d[O+24]), "+f"(d[O+25]), "+f"(d[O+26]), "+f"(d[O+27]), "+f"(d[O+28]), "+f"(d[O+29]), "+f"(d[O+30]), "+f"(d[O+31]), "+f"(d[O+32]), "+f"(d[O+33]), "+f"(d[O+34]), "+f"(d[O+35]), "+f"(d[O+36]), "+f"(d[O+37]), "+f"(d[O+38]), "+f"(d[O+39]), "+f"(d[O+40]), "+f"(d[O+41]), "+f"(d[O+42]), "+f"(d[O+43]), "+f"(d[O+44]), "+f"(d[O+45]), "+f"(d[O+46]), "+f"(d[O+47]), "+f"(d[O+48]), "+f"(d[O+49]), "+f"(d[O+50]), "+f"(d[O+51]), "+f"(d[O+52]), "+f"(d[O+53]), "+f"(d[O+54]), "+f"(d[O+55]), "+f"(d[O+56]), "+f"(d[O+57]), "+f"(d[O+58]), "+f"(d[O+59]), "+f"(d[O+60]), "+f"(d[O+61]), "+f"(d[O+62]), "+f"(d[O+63])
   : "l"(da), "l"(db), "n"(TB & 1), "n"(TB >> 1));
  else if constexpr (ACC == 0) asm volatile("wgmma.mma_async.sync.aligned.m64n128k16.f32.bf16.bf16 {%0,%1,%2,%3,%4,%5,%6,%7,%8,%9,%10,%11,%12,%13,%14,%15,%16,%17,%18,%19,%20,%21,%22,%23,%24,%25,%26,%27,%28,%29,%30,%31,%32,%33,%34,%35,%36,%37,%38,%39,%40,%41,%42,%43,%44,%45,%46,%47,%48,%49,%50,%51,%52,%53,%54,%55,%56,%57,%58,%59,%60,%61,%62,%63}, %64, %65, 0, 1, 1, %67, %66;"
   : "=f"(d[O+0]), "=f"(d[O+1]), "=f"(d[O+2]), "=f"(d[O+3]), "=f"(d[O+4]), "=f"(d[O+5]), "=f"(d[O+6]), "=f"(d[O+7]), "=f"(d[O+8]), "=f"(d[O+9]), "=f"(d[O+10]), "=f"(d[O+11]), "=f"(d[O+12]), "=f"(d[O+13]), "=f"(d[O+14]), "=f"(d[O+15]), "=f"(d[O+16]), "=f"(d[O+17]), "=f"(d[O+18]), "=f"(d[O+19]), "=f"(d[O+20]), "=f"(d[O+21]), "=f"(d[O+22]), "=f"(d[O+23]), "=f"(d[O+24]), "=f"(d[O+25]), "=f"(d[O+26]), "=f"(d[O+27]), "=f"(d[O+28]), "=f"(d[O+29]), "=f"(d[O+30]), "=f"(d[O+31]), "=f"(d[O+32]), "=f"(d[O+33]), "=f"(d[O+34]), "=f"(d[O+35]), "=f"(d[O+36]), "=f"(d[O+37]), "=f"(d[O+38]), "=f"(d[O+39]), "=f"(d[O+40]), "=f"(d[O+41]), "=f"(d[O+42]), "=f"(d[O+43]), "=f"(d[O+44]), "=f"(d[O+45]), "=f"(d[O+46]), "=f"(d[O+47]), "=f"(d[O+48]), "=f"(d[O+49]), "=f"(d[O+50]), "=f"(d[O+51]), "=f"(d[O+52]), "=f"(d[O+53]), "=f"(d[O+54]), "=f"(d[O+55]), "=f"(d[O+56]), "=f"(d[O+57]), "=f"(d[O+58]), "=f"(d[O+59]), "=f"(d[O+60]), "=f"(d[O+61]), "=f"(d[O+62]), "=f"(d[O+63])
   : "l"(da), "l"(db), "n"(TB & 1), "n"(TB >> 1));
  else asm volatile("{\n.reg .pred p;\nsetp.ne.b32 p, %68, 0;\nwgmma.mma_async.sync.aligned.m64n128k16.f32.bf16.bf16 {%0,%1,%2,%3,%4,%5,%6,%7,%8,%9,%10,%11,%12,%13,%14,%15,%16,%17,%18,%19,%20,%21,%22,%23,%24,%25,%26,%27,%28,%29,%30,%31,%32,%33,%34,%35,%36,%37,%38,%39,%40,%41,%42,%43,%44,%45,%46,%47,%48,%49,%50,%51,%52,%53,%54,%55,%56,%57,%58,%59,%60,%61,%62,%63}, %64, %65, p, 1, 1, %67, %66;\n}"
   : "+f"(d[O+0]), "+f"(d[O+1]), "+f"(d[O+2]), "+f"(d[O+3]), "+f"(d[O+4]), "+f"(d[O+5]), "+f"(d[O+6]), "+f"(d[O+7]), "+f"(d[O+8]), "+f"(d[O+9]), "+f"(d[O+10]), "+f"(d[O+11]), "+f"(d[O+12]), "+f"(d[O+13]), "+f"(d[O+14]), "+f"(d[O+15]), "+f"(d[O+16]), "+f"(d[O+17]), "+f"(d[O+18]), "+f"(d[O+19]), "+f"(d[O+20]), "+f"(d[O+21]), "+f"(d[O+22]), "+f"(d[O+23]), "+f"(d[O+24]), "+f"(d[O+25]), "+f"(d[O+26]), "+f"(d[O+27]), "+f"(d[O+28]), "+f"(d[O+29]), "+f"(d[O+30]), "+f"(d[O+31]), "+f"(d[O+32]), "+f"(d[O+33]), "+f"(d[O+34]), "+f"(d[O+35]), "+f"(d[O+36]), "+f"(d[O+37]), "+f"(d[O+38]), "+f"(d[O+39]), "+f"(d[O+40]), "+f"(d[O+41]), "+f"(d[O+42]), "+f"(d[O+43]), "+f"(d[O+44]), "+f"(d[O+45]), "+f"(d[O+46]), "+f"(d[O+47]), "+f"(d[O+48]), "+f"(d[O+49]), "+f"(d[O+50]), "+f"(d[O+51]), "+f"(d[O+52]), "+f"(d[O+53]), "+f"(d[O+54]), "+f"(d[O+55]), "+f"(d[O+56]), "+f"(d[O+57]), "+f"(d[O+58]), "+f"(d[O+59]), "+f"(d[O+60]), "+f"(d[O+61]), "+f"(d[O+62]), "+f"(d[O+63])
   : "l"(da), "l"(db), "n"(TB & 1), "n"(TB >> 1), "r"(sd));
}
template<int O,int TB,int ACC,int NN> __device__ __forceinline__ void mma_rs128(float (&d)[NN], uint32_t a0, uint32_t a1, uint32_t a2, uint32_t a3, uint64_t db, int sd = 0){
  if constexpr (ACC == 1) asm volatile("wgmma.mma_async.sync.aligned.m64n128k16.f32.bf16.bf16 {%0,%1,%2,%3,%4,%5,%6,%7,%8,%9,%10,%11,%12,%13,%14,%15,%16,%17,%18,%19,%20,%21,%22,%23,%24,%25,%26,%27,%28,%29,%30,%31,%32,%33,%34,%35,%36,%37,%38,%39,%40,%41,%42,%43,%44,%45,%46,%47,%48,%49,%50,%51,%52,%53,%54,%55,%56,%57,%58,%59,%60,%61,%62,%63}, {%64,%65,%66,%67}, %68, 1, 1, 1, %69;"
   : "+f"(d[O+0]), "+f"(d[O+1]), "+f"(d[O+2]), "+f"(d[O+3]), "+f"(d[O+4]), "+f"(d[O+5]), "+f"(d[O+6]), "+f"(d[O+7]), "+f"(d[O+8]), "+f"(d[O+9]), "+f"(d[O+10]), "+f"(d[O+11]), "+f"(d[O+12]), "+f"(d[O+13]), "+f"(d[O+14]), "+f"(d[O+15]), "+f"(d[O+16]), "+f"(d[O+17]), "+f"(d[O+18]), "+f"(d[O+19]), "+f"(d[O+20]), "+f"(d[O+21]), "+f"(d[O+22]), "+f"(d[O+23]), "+f"(d[O+24]), "+f"(d[O+25]), "+f"(d[O+26]), "+f"(d[O+27]), "+f"(d[O+28]), "+f"(d[O+29]), "+f"(d[O+30]), "+f"(d[O+31]), "+f"(d[O+32]), "+f"(d[O+33]), "+f"(d[O+34]), "+f"(d[O+35]), "+f"(d[O+36]), "+f"(d[O+37]), "+f"(d[O+38]), "+f"(d[O+39]), "+f"(d[O+40]), "+f"(d[O+41]), "+f"(d[O+42]), "+f"(d[O+43]), "+f"(d[O+44]), "+f"(d[O+45]), "+f"(d[O+46]), "+f"(d[O+47]), "+f"(d[O+48]), "+f"(d[O+49]), "+f"(d[O+50]), "+f"(d[O+51]), "+f"(d[O+52]), "+f"(d[O+53]), "+f"(d[O+54]), "+f"(d[O+55]), "+f"(d[O+56]), "+f"(d[O+57]), "+f"(d[O+58]), "+f"(d[O+59]), "+f"(d[O+60]), "+f"(d[O+61]), "+f"(d[O+62]), "+f"(d[O+63])
   : "r"(a0), "r"(a1), "r"(a2), "r"(a3), "l"(db), "n"(TB));
  else if constexpr (ACC == 0) asm volatile("wgmma.mma_async.sync.aligned.m64n128k16.f32.bf16.bf16 {%0,%1,%2,%3,%4,%5,%6,%7,%8,%9,%10,%11,%12,%13,%14,%15,%16,%17,%18,%19,%20,%21,%22,%23,%24,%25,%26,%27,%28,%29,%30,%31,%32,%33,%34,%35,%36,%37,%38,%39,%40,%41,%42,%43,%44,%45,%46,%47,%48,%49,%50,%51,%52,%53,%54,%55,%56,%57,%58,%59,%60,%61,%62,%63}, {%64,%65,%66,%67}, %68, 0, 1, 1, %69;"
   : "=f"(d[O+0]), "=f"(d[O+1]), "=f"(d[O+2]), "=f"(d[O+3]), "=f"(d[O+4]), "=f"(d[O+5]), "=f"(d[O+6]), "=f"(d[O+7]), "=f"(d[O+8]), "=f"(d[O+9]), "=f"(d[O+10]), "=f"(d[O+11]), "=f"(d[O+12]), "=f"(d[O+13]), "=f"(d[O+14]), "=f"(d[O+15]), "=f"(d[O+16]), "=f"(d[O+17]), "=f"(d[O+18]), "=f"(d[O+19]), "=f"(d[O+20]), "=f"(d[O+21]), "=f"(d[O+22]), "=f"(d[O+23]), "=f"(d[O+24]), "=f"(d[O+25]), "=f"(d[O+26]), "=f"(d[O+27]), "=f"(d[O+28]), "=f"(d[O+29]), "=f"(d[O+30]), "=f"(d[O+31]), "=f"(d[O+32]), "=f"(d[O+33]), "=f"(d[O+34]), "=f"(d[O+35]), "=f"(d[O+36]), "=f"(d[O+37]), "=f"(d[O+38]), "=f"(d[O+39]), "=f"(d[O+40]), "=f"(d[O+41]), "=f"(d[O+42]), "=f"(d[O+43]), "=f"(d[O+44]), "=f"(d[O+45]), "=f"(d[O+46]), "=f"(d[O+47]), "=f"(d[O+48]), "=f"(d[O+49]), "=f"(d[O+50]), "=f"(d[O+51]), "=f"(d[O+52]), "=f"(d[O+53]), "=f"(d[O+54]), "=f"(d[O+55]), "=f"(d[O+56]), "=f"(d[O+57]), "=f"(d[O+58]), "=f"(d[O+59]), "=f"(d[O+60]), "=f"(d[O+61]), "=f"(d[O+62]), "=f"(d[O+63])
   : "r"(a0), "r"(a1), "r"(a2), "r"(a3), "l"(db), "n"(TB));
  else asm volatile("{\n.reg .pred p;\nsetp.ne.b32 p, %70, 0;\nwgmma.mma_async.sync.aligned.m64n128k16.f32.bf16.bf16 {%0,%1,%2,%3,%4,%5,%6,%7,%8,%9,%10,%11,%12,%13,%14,%15,%16,%17,%18,%19,%20,%21,%22,%23,%24,%25,%26,%27,%28,%29,%30,%31,%32,%33,%34,%35,%36,%37,%38,%39,%40,%41,%42,%43,%44,%45,%46,%47,%48,%49,%50,%51,%52,%53,%54,%55,%56,%57,%58,%59,%60,%61,%62,%63}, {%64,%65,%66,%67}, %68, p, 1, 1, %69;\n}"
   : "+f"(d[O+0]), "+f"(d[O+1]), "+f"(d[O+2]), "+f"(d[O+3]), "+f"(d[O+4]), "+f"(d[O+5]), "+f"(d[O+6]), "+f"(d[O+7]), "+f"(d[O+8]), "+f"(d[O+9]), "+f"(d[O+10]), "+f"(d[O+11]), "+f"(d[O+12]), "+f"(d[O+13]), "+f"(d[O+14]), "+f"(d[O+15]), "+f"(d[O+16]), "+f"(d[O+17]), "+f"(d[O+18]), "+f"(d[O+19]), "+f"(d[O+20]), "+f"(d[O+21]), "+f"(d[O+22]), "+f"(d[O+23]), "+f"(d[O+24]), "+f"(d[O+25]), "+f"(d[O+26]), "+f"(d[O+27]), "+f"(d[O+28]), "+f"(d[O+29]), "+f"(d[O+30]), "+f"(d[O+31]), "+f"(d[O+32]), "+f"(d[O+33]), "+f"(d[O+34]), "+f"(d[O+35]), "+f"(d[O+36]), "+f"(d[O+37]), "+f"(d[O+38]), "+f"(d[O+39]), "+f"(d[O+40]), "+f"(d[O+41]), "+f"(d[O+42]), "+f"(d[O+43]), "+f"(d[O+44]), "+f"(d[O+45]), "+f"(d[O+46]), "+f"(d[O+47]), "+f"(d[O+48]), "+f"(d[O+49]), "+f"(d[O+50]), "+f"(d[O+51]), "+f"(d[O+52]), "+f"(d[O+53]), "+f"(d[O+54]), "+f"(d[O+55]), "+f"(d[O+56]), "+f"(d[O+57]), "+f"(d[O+58]), "+f"(d[O+59]), "+f"(d[O+60]), "+f"(d[O+61]), "+f"(d[O+62]), "+f"(d[O+63])
   : "r"(a0), "r"(a1), "r"(a2), "r"(a3), "l"(db), "n"(TB), "r"(sd));
}

#define NEARLY 0
#define XAHEAD 3
#define HEADN 6
#define WBATCH 1
#define WB 8
#define WSLEEP 20
#define XSPREAD 4
#define NOSEND 0
#define MSPLIT 3
#define PFALL 1
#define L2PF 1
#define STAG 0
#define EPF 2
#define XNB 2
#define FNB 0
#define GNB 0
#define TH 5
#define PF0 4
#define FSPLIT 1
#define MGLU 1
#define SPC 2
#define TL 13
#define SPACE 40
#define WPF 1
#define WAFTER 7
#define WPACE 0
#define GATE_AT 4
#define TPACE 40
#define PFMODE 0
#define MAPMODE 1
template <int V> struct IC { static constexpr int value = V; };
struct Maps { CUtensorMap x, ft, g64, u64, e, wr, wi, xs, ts, t, g32, u32, d224, o; };

constexpr int NCTA = 130;
constexpr int U = 16384;
constexpr int TB = 36864;
constexpr int OFF_RING = 8 * U, OFF_Z = 12 * U, OFF_XB = 12 * U, OFF_T = 13 * U, OFF_D = OFF_T;
constexpr int OFF_BAR = 14 * U, OFF_SP = OFF_BAR + 512, OFF_G = OFF_SP + 1024 + 128;
constexpr int SMEM_BYTES = OFF_G + 512;
constexpr int B_FX = 0, B_FA = 8, B_FT = 12, B_Z = 16, B_W = 24, B_HX = 25, B_TL = 26, B_HP = 27, B_WR = 30, B_E0 = 34;
constexpr int B_EA = 35, B_ET = 39, B_PZ = 43, B_RDY = 45, B_FE = 46;
constexpr int B_T = 50, B_XS = 51, B_G = 53, B_RD0 = 54, NBAR = 55;
__host__ __device__ constexpr int rslot(int n) { return n & 3; }
__host__ __device__ constexpr int rpar(int n) { return (n >> 2) & 1; }

__global__ void __cluster_dims__(2, 1, 1) __launch_bounds__(512, 1)
fused_kernel(Work* __restrict__ ws, const uint16_t* __restrict__ dtab, const __nv_bfloat16* __restrict__ w_r, const __nv_bfloat16* __restrict__ w_i,
             const __nv_bfloat16* __restrict__ gate_w, const __nv_bfloat16* __restrict__ x, const __grid_constant__ Maps maps) {
  extern __shared__ __align__(1024) uint8_t smem[];
  if (threadIdx.x < 32 && elect_one()) {
#pragma unroll
    for (int i = 0; i < PF0; i++) asm volatile("prefetch.tensormap [%0];" ::"l"((const char*)&maps + i * 128) : "memory");
  }
  const uint32_t sb = smem_u32(smem);
  const uint32_t bars = sb + OFF_BAR;
  const int tid = threadIdx.x, lane = tid & 31;
  const int warp = __shfl_sync(0xffffffffu, tid >> 5, 0);
  const bool helper = blockIdx.x >= 128;
  const int cl = (blockIdx.x >> 1) & 63, rank = blockIdx.x & 1;
  const int q4 = (cl & 1) | ((cl >> 2) & 2), rb = ((cl >> 1) & 3) | ((cl >> 4) << 2);
  const int j = 2 * q4 + rank;
  const int f_full = 448 * q4 + (rank ? 256 : 0);
  const int f_half = 448 * q4 + (rank ? 224 : 192);
  const int kg = 2 * j + (rb >> 3), tn = rb & 7;

  if (tid == 64) { PROF_EV(0); PROF_CK(40); }
  if (warp < 8) {
    if (!helper && tid < 32) {
      const int r = 16 * j + (tid & 15);
      asm volatile("prefetch.global.L2 [%0];" ::"l"(x + (size_t)(2 * rb + (r >> 6) + 32 * (r & 63)) * 512 + 64 * (tid >> 4)));
    }
    asm volatile("barrier.cluster.arrive.relaxed.aligned;" ::: "memory");
    asm volatile("setmaxnreg.inc.sync.aligned.u32 192;");
    if (!helper) {
      const int wg = warp >> 2, w = warp & 3, g = lane >> 2;
      const bool elect = (tid & 127) == 0;
      float cX[32], cA[64], cB[64], cC[64], ci[64], ct[64];
      const int zero = blockIdx.x >> 16;
      uint32_t h[56], yf[16];
      const uint32_t d0 = (sb & 0x3FFFF) >> 4;
      const uint32_t dK = d0 | (1u << 16), dN = d0 | (512u << 16);
      const uint32_t dX = dK + wg * 512;
      constexpr uint32_t RING = OFF_RING >> 4;
      auto waitA = [&](int n) { mbar_wait(bars + 8 * (B_FA + rslot(n)), rpar(n)); };
      auto freeA = [&](int n) { mbar_arrive_if(elect, bars + 8 * (B_EA + rslot(n))); };
      auto nop = [] {};

      asm volatile("bar.sync 0, 384;" ::: "memory");
#pragma unroll 1
      for (int i = 0; i < 4; i++) {
        const uint64_t dx = d128(dX + i * 2048), df = d128(dK + (OFF_XB >> 4) + (i & 1) * 1024);
        mbar_wait(bars + 8 * (B_FX + 2 * i), 0);
        wg_fence();
        mma_ss64<0, 0, 2>(cX, df, dx, i);
        mma_ss64<0, 0, 1>(cX, df + 2, dx + 2);
        wg_commit(); wg_wait<1>();
        mbar_arrive_if(elect && i, bars + 8 * (B_EA + rslot(i - 1)));
        mma_ss64<0, 0, 1>(cX, df + 4, dx + 4);
        mma_ss64<0, 0, 1>(cX, df + 6, dx + 6);
        if (i == 0 && tid == 0) PROF_EV(1);
        mbar_wait(bars + 8 * (B_FX + 2 * i + 1), 0);
        wg_fence();
#pragma unroll
        for (int k = 0; k < 4; k++) mma_ss64<0, 0, 1>(cX, df + (512 + k * 2), dx + (1024 + k * 2));
        wg_commit();
        waitA(i);
        wg_fence();
        const uint64_t da = d128(dX + i * 1024), db = d128(dN + RING + i * 1024);
        mma_ss128<0, 1, 2>(cA, da, db, i);
        wg_commit(); wg_wait<1>();
        mbar_arrive_if(elect, bars + 8 * (B_FE + i));
#pragma unroll
        for (int k = 1; k < 4; k++) mma_ss128<0, 1, 1>(cA, da + k * 2, db + k * 128);
        wg_commit();
      }
      fence_regs<0, 32>(cX);
#pragma unroll
      for (int e = 0; e < 16; e++) yf[e] = pack_pin(cX[2 * e], cX[2 * e + 1]);
      if (tid == 0) { PROF_EV(2); PROF_CK(42); }
      {
        waitA(4); mbar_wait(bars + 8 * B_E0, 0);
        const uint64_t de = d128(dN + (wg ? RING : OFF_XB >> 4));
        wg_fence();
        mma_rs128<0, 1, 0>(cB, yf[0], yf[1], yf[2], yf[3], de);
        wg_commit();
        wg_wait<1>();
        freeA(3);
#pragma unroll
        for (int k = 1; k < 4; k++) mma_rs128<0, 1, 1>(cB, yf[4 * k], yf[4 * k + 1], yf[4 * k + 2], yf[4 * k + 3], de + k * 128);
        wg_commit();
      }
      bool rel = false;
      auto acquire = [&](int n) {
        rel = elect;
        if (!mbar_try(bars + 8 * (B_FA + rslot(n)), rpar(n))) { wg_wait<0>(); freeA(n - 1); rel = false; waitA(n); }
      };
      auto freeP = [&](int n) { mbar_arrive_if(rel, bars + 8 * (B_EA + rslot(n - 1))); };
      auto ffn_step = [&](auto first, auto split, float (&acc)[64], int n, int kb, auto done, auto work) {
        constexpr int SPLIT = decltype(split)::value;
        acquire(n);
        wg_fence();
        const uint64_t dx = d128(dX + kb * 1024), db = d128(dN + RING + rslot(n) * 1024);
        mma_ss128<0, 1, decltype(first)::value>(acc, dx, db, kb);
#pragma unroll
        for (int k = 1; k < SPLIT; k++) mma_ss128<0, 1, 1>(acc, dx + k * 2, db + k * 128);
        wg_commit();
        work();
        wg_wait<1>();
        freeP(n);
        done();
        if (SPLIT < 4) {
          wg_fence();
#pragma unroll
          for (int k = SPLIT; k < 4; k++) mma_ss128<0, 1, 1>(acc, dx + k * 2, db + k * 128);
          wg_commit();
        }
      };
      {
        const int s0 = 2 * rb + wg, kr = 2 * ((s0 & 1) | ((s0 & 4) >> 1));
        const int m = lane >> 3, r = lane & 7;
        const uint32_t a0 = sb + OFF_XB + wg * 8192 + (((w >> 1) * 8 + (m >> 1)) * 2 + (w & 1)) * 256 + (m & 1) * 128 + ((r ^ (kr + (m & 1))) << 4);
        ffn_step(IC<1>(), IC<4>(), cA, 5, 4, [&] { fence_regs<0, 64>(cB); }, nop);
        asm volatile("bar.sync 5, 256;" ::: "memory");
        auto stage = [&](int i) {
          stsm4t(a0 + i * 1024, pack_bf16(cB[8 * i] - cB[34 + 8 * i], cB[8 * i + 1] - cB[35 + 8 * i]),
                 pack_bf16(cB[32 + 8 * i] + cB[8 * i + 2], cB[33 + 8 * i] + cB[8 * i + 3]),
                 pack_bf16(cB[8 * i + 4] - cB[38 + 8 * i], cB[8 * i + 5] - cB[39 + 8 * i]),
                 pack_bf16(cB[36 + 8 * i] + cB[8 * i + 6], cB[37 + 8 * i] + cB[8 * i + 7]));
          if (j == 0 && w == 0) {
            const uint32_t a1 = r ? sb + OFF_SP + 1024 : sb + OFF_SP + wg * 512 + (m & 1) * 256 + (m >> 1) * 128;
#pragma unroll
            for (int n = 2 * i; n < 2 * i + 2; n++)
              asm volatile("stmatrix.sync.aligned.m8n8.x4.shared.b16 [%0], {%1,%2,%3,%4};" ::"r"(a1 + ((n ^ (kr + (m >> 1)) ^ r) << 4)),
                           "r"(pack_bf16(cB[4 * n], cB[4 * n + 1])), "r"(pack_bf16(cB[4 * n + 2], cB[4 * n + 3])),
                           "r"(pack_bf16(cB[32 + 4 * n], cB[33 + 4 * n])), "r"(pack_bf16(cB[34 + 4 * n], cB[35 + 4 * n])) : "memory");
          }
        };
        auto publish = [&] {
          asm volatile("fence.proxy.async.shared::cta;" ::: "memory");
          __syncwarp();
          mbar_arrive_if(lane == 0, bars + 8 * (B_XS + wg));
          if (tid == 0) PROF_EV(3);
        };
        stage(0);
        ffn_step(IC<1>(), IC<FSPLIT>(), cA, 6, 5, nop, nop);
        stage(1);
        ffn_step(IC<1>(), IC<FSPLIT>(), cA, 7, 6, nop, nop);
        stage(2);
        ffn_step(IC<1>(), IC<2>(), cA, 8, 7, [&] { stage(3); }, nop);
        publish();
      }
      float g0 = 0.f, g1 = 0.f;
      uint32_t tag = 0;
      uint32_t ob[2] = {0, 0};
      auto glu = [&](auto& acc, int half, int ho, int i0, int i1) {
#pragma unroll
        for (int i = i0; i < i1; i++)
          asm volatile("{\n.reg .b32 a, b;\ncvt.rn.relu.bf16x2.f32 a, %2, %1;\ncvt.rn.bf16x2.f32 b, %4, %3;\nmul.rn.bf16x2 a, a, b;\nmul.rn.bf16x2 %0, a, %5;\n}"
                       : "=r"(h[ho + i]) : "f"(acc[2 * i]), "f"(acc[2 * i + 1]), "f"(acc[half + 2 * i]), "f"(acc[half + 1 + 2 * i]), "r"(ob[i & 1]) : "memory");
      };
      ffn_step(IC<2>(), IC<1>(), cB, 9, zero, nop, nop);
#pragma unroll 1
      for (int kb = 1; kb < 8; kb++)
        ffn_step(IC<1>(), IC<FSPLIT>(), cB, 9 + kb, kb, nop, [&] {
          if (kb == 4 + 2 * wg) {
            mbar_wait(bars + 8 * B_G, 0);
            const uint32_t gb0 = *(const uint32_t*)(smem + OFF_G + (wg * 64 + w * 16 + g) * 4), gb1 = *(const uint32_t*)(smem + OFF_G + (wg * 64 + w * 16 + g + 8) * 4);
            tag = gb0 & 1; g0 = __uint_as_float(gb0 & ~1u); g1 = __uint_as_float(gb1 & ~1u);
            ob[0] = pack_bf16(1.0f - g0, 1.0f - g0); ob[1] = pack_bf16(1.0f - g1, 1.0f - g1);
            glu(cA, 32, 0, 0, 16);
          }
        });
      if (tid == 0) { PROF_EV(4); PROF_CK(43); }
      auto m_step = [&](auto first, int i) {
        acquire(17 + i);
        wg_fence();
        const uint64_t dx = d128(dX + i * 2048), dm = d64(dN + RING + rslot(17 + i) * 1024);
        mma_ss64<0, 1, decltype(first)::value>(ct, dx, dm);
#pragma unroll
        for (int k = 1; k < MSPLIT; k++) mma_ss64<0, 1, 1>(ct, dx + ((k >> 2) * 1024 + (k & 3) * 2), dm + k * 64);
        wg_commit();
        wg_wait<1>();
        freeP(17 + i);
        wg_fence();
#pragma unroll
        for (int k = MSPLIT; k < 8; k++) mma_ss64<0, 1, 1>(ct, dx + ((k >> 2) * 1024 + (k & 3) * 2), dm + k * 64);
        wg_commit();
      };
      m_step(IC<0>(), 0);
#pragma unroll 1
      for (int i = 1; i < 5; i++) {
        if (i == 1 + 2 * wg) glu(cB, 32, 16, 0, 16);
        if (i < 4) m_step(IC<1>(), i);
      }
      if (tid == 0) { PROF_EV(5); PROF_CK(44); }
      ffn_step(IC<0>(), IC<1>(), cC, 21, 0, nop, nop);
#pragma unroll 1
      for (int kb = 1; kb < 8; kb++)
        ffn_step(IC<1>(), IC<FSPLIT>(), cC, 21 + kb, kb, [&] { mbar_arrive_if(elect && !(kb & 1), bars + 8 * (B_ET + (kb >> 1) - 1)); }, [&] {
          if (kb == 1 + wg) glu(ct, 16, 48, 0, 8);
        });

      auto twait = [&](uint32_t bar, uint32_t par, int) { mbar_wait(bar, par); };
      const int fo = warp * 128 + lane;
      auto fetch = [&](uint4 (&pv)[4], int z) {
        twait(bars + 8 * (z < 4 ? B_Z + 2 * z + wg : B_HP + z - 4), 0, 8 + z);
        const uint8_t* src = smem + (z < 4 ? OFF_Z - z * U : z == 4 ? OFF_T : (z - 5) * U) + fo * 16;
#pragma unroll
        for (int i = 0; i < 4; i++) pv[i] = *(const uint4*)(src + i * 512);
      };
      auto check = [&](uint4 (&pv)[4], int z) {
        const uint32_t t0 = (uint32_t)clock();
        while (__any_sync(0xffffffffu, ((pv[0].x ^ tag) | (pv[1].x ^ tag) | (pv[2].x ^ tag) | (pv[3].x ^ tag)) & 1)) {
#pragma unroll
          for (int i = 0; i < 4; i++) pv[i] = ld_x4(ws->part + (size_t)((rb * 8 + j) * 3 + z - 4) * 1024 + fo + i * 32);
          spin_guard(t0);
        }
#pragma unroll
        for (int i = 0; i < 4; i++) pv[i].x &= ~1u;
      };
      const uint32_t peerZ = mapa(sb + OFF_Z + fo * 16, rank ^ 1), peerB = mapa(bars + 8 * (B_Z + wg), rank ^ 1);
      auto tile_mma = [&](auto off, int t, int k0, int k1, int init) {
        constexpr int O = decltype(off)::value;
        const uint64_t db = d128(dN + (t & 3) * (TB >> 4)), dw = db + rank * 256, dm = db + (rank ? 0 : 1536);
#pragma unroll
        for (int k = k0; k < k1; k++) {
          if (k == 0) mma_rs64<O, 1, 2>(ct, h[0], h[1], h[2], h[3], dw, init);
          else if (k < 14) mma_rs64<O, 1, 1>(ct, h[4 * k], h[4 * k + 1], h[4 * k + 2], h[4 * k + 3], k < 12 ? dw + k * 128 : dm + (k - 12) * 128);
          else mma_rs64<O, 1, 1>(ct, yf[4 * k - 56], yf[4 * k - 55], yf[4 * k - 54], yf[4 * k - 53], db + k * 128);
        }
      };
      uint4 pv[4];
      auto tile = [&](auto off, int t) {
        constexpr int P = 32 - decltype(off)::value;
        const bool grid = t >= 4 && t < 7, pre = t != 1 && t != 5;
        const int zo = grid ? t - 4 : t == 7 ? 3 : t - 1, z = t - 2;
        const int owner = rb * 8 + 2 * ((q4 + zo + 1) & 3) + rank;
        uint4* dst = ws->part + (size_t)(owner * 3 + zo) * 1024 + fo;
        const uint32_t src = sb + (z < 4 ? OFF_Z - z * U : z == 4 ? OFF_T : (z - 5) * U) + fo * 16;
        twait(bars + 8 * (B_FT + (t & 3)), t >> 2, t);
        wg_fence();
        tile_mma(off, t, 0, TH, t >= 3 && t != 6);
        wg_commit();
        wg_wait<1>();
        mbar_arrive_if(elect && t < 6, bars + 8 * (B_ET + t - 1));
        if (t < 3) twait(bars + 8 * (t == 1 ? B_RD0 : B_RDY), 0, 14 + t);
        fence_regs<P, 32>(ct);
        uint32_t pk[16];
#pragma unroll
        for (int i = 0; i < 16; i++) pk[i] = pack_bf16(ct[P + 2 * i], ct[P + 2 * i + 1]);
        wg_fence();
#pragma unroll
        for (int i = 0; i < 4; i++) {
          asm volatile(
              "{\n.reg .pred p;\nsetp.ne.b32 p, %7, 0;\n@p st.relaxed.gpu.global.v4.u32 [%0], {%3,%4,%5,%6};\n"
              "@!p st.async.weak.shared::cluster.mbarrier::complete_tx::bytes.v4.b32 [%1], {%3,%4,%5,%6}, [%2];\n}" ::"l"(dst + i * 32),
              "r"(peerZ - zo * U + i * 512), "r"(peerB + 16 * zo), "r"((pk[4 * i] & ~(uint32_t)grid) | (tag & grid)), "r"(pk[4 * i + 1]), "r"(pk[4 * i + 2]),
              "r"(pk[4 * i + 3]), "r"((int)grid) : "memory");
          if (i == 3) hint_add_if(grid && lane == 0, &ws->cntP[32 * owner + zo]);
          tile_mma(off, t, TH + SPC * i, i < 3 ? TH + SPC * i + SPC : TL, 0);
        }
        wg_commit();
        if (pre) twait(bars + 8 * (z < 4 ? B_Z + 2 * z + wg : B_HP + z - 4), 0, 8 + z);
        wg_fence();
#pragma unroll
        for (int i = 0; i < 4; i++) {
          asm volatile("{\n.reg .pred p;\nsetp.ne.b32 p, %5, 0;\n@p ld.shared.v4.u32 {%0,%1,%2,%3}, [%4];\n}"
                       : "=r"(pv[i].x), "=r"(pv[i].y), "=r"(pv[i].z), "=r"(pv[i].w) : "r"(src + i * 512), "r"((int)pre) : "memory");
          tile_mma(off, t, TL + i, i < 3 ? TL + 1 + i : 18, 0);
        }
        wg_commit();
        if (pre && t != 7) {
          if (z >= 4) check(pv, z);
#pragma unroll
          for (int i = 0; i < 4; i++) {
            const uint32_t a[4] = {pv[i].x, pv[i].y, pv[i].z, pv[i].w};
#pragma unroll
            for (int e = 0; e < 4; e++) { ct[P + 8 * i + 2 * e] = bf_lo(a[e]); ct[P + 8 * i + 2 * e + 1] = bf_hi(a[e]); }
          }
        }
      };
      asm volatile("barrier.cluster.wait.aligned;" ::: "memory");
      twait(bars + 8 * B_FT, 0, 0);
      wg_fence();
      tile_mma(IC<0>(), 0, 0, 5, zero);
      wg_commit();
      wg_wait<1>();
      mbar_arrive_if(elect, bars + 8 * (B_ET + 3));
      glu(cC, 32, 32, 0, 8);
      waitA(29 + wg);
      wg_fence();
      tile_mma(IC<0>(), 0, 5, 8, 0);
      tile_mma(IC<0>(), 0, 12, 14, 0);
      wg_commit();
      glu(cC, 32, 32, 8, 16);
      if (tid == 0) PROF_EV(6);
      if (tid == 128) PROF_EV(27);
      mbar_wait(bars + 8 * (j == 0 ? B_T : B_TL), 0);
      if (tid == 0) { PROF_EV(7); PROF_CK(45); }
      wg_fence();
      {
        const uint64_t dt = d128(dN + (OFF_T >> 4) + wg * 512), de = d128(dK + RING + (1 + wg) * 1024);
        mma_ss64<0, 1, 0>(ci, de, dt);
        mma_ss64<32, 1, 0>(ci, de + 512, dt);
#pragma unroll
        for (int k = 1; k < 4; k++) {
          mma_ss64<0, 1, 1>(ci, de + k * 2, dt + k * 128);
          mma_ss64<32, 1, 1>(ci, de + (512 + k * 2), dt + k * 128);
        }
        wg_commit();
      }
      tile_mma(IC<0>(), 0, 8, 12, 0);
      wg_commit();
      wg_wait<1>();
      if (elect) asm volatile("mbarrier.arrive.shared::cluster.b64 _, [%0];" ::"r"(mapa(bars + 8 * B_RDY, rank ^ 1)) : "memory");
      mbar_arrive_if(elect, bars + 8 * (B_PZ + 1));
      fence_regs<0, 64>(ci);
#pragma unroll
      for (int i = 0; i < 16; i++) {
        const float gg = ((i & 1) ? g1 : g0) * (2.0f / (2048.0f * 512.0f));
        if (i & 2) yf[i] = pack_pin((ci[2 * i] - ci[28 + 2 * i]) * gg, (ci[2 * i + 1] - ci[29 + 2 * i]) * gg);
        else yf[i] = pack_pin((ci[2 * i] + ci[36 + 2 * i]) * gg, (ci[2 * i + 1] + ci[37 + 2 * i]) * gg);
      }
      wg_fence();
      tile_mma(IC<0>(), 0, 14, 18, 0);
      wg_commit();
      if (tid == 0) PROF_EV(8);
      if (tid == 128) PROF_EV(28);
#pragma unroll 1
      for (int t = 1;; t += 2) {
        tile(IC<32>(), t);
        if (t == 7) break;
        tile(IC<0>(), t + 1);
      }
      if (tid == 0) { PROF_EV(9); PROF_CK(46); }
      if (tid == 128) PROF_EV(29);
      {
        uint4 p2[4], p3[4];
        fetch(p3, 3);
        if (tid == 0) PROF_EV(25);
        fetch(p2, 6);
        if (tid == 0) PROF_EV(24);
        check(pv, 5); check(p2, 6);
        uint32_t ps[16];
#pragma unroll
        for (int i = 0; i < 4; i++) {
          const uint32_t a[4] = {pv[i].x, pv[i].y, pv[i].z, pv[i].w}, b[4] = {p2[i].x, p2[i].y, p2[i].z, p2[i].w}, c[4] = {p3[i].x, p3[i].y, p3[i].z, p3[i].w};
#pragma unroll
          for (int e = 0; e < 4; e++) asm("{\n.reg .b32 t;\nadd.rn.bf16x2 t, %1, %2;\nadd.rn.bf16x2 %0, t, %3;\n}" : "=r"(ps[4 * i + e]) : "r"(a[e]), "r"(c[e]), "r"(b[e]));
        }
        if (tid == 0) PROF_EV(14);
        wg_wait<0>();
        fence_regs<32, 32>(ct);
        float sum[32];
#pragma unroll
        for (int i = 0; i < 16; i++) { sum[2 * i] = ct[32 + 2 * i] + bf_lo(ps[i]); sum[2 * i + 1] = ct[33 + 2 * i] + bf_hi(ps[i]); }
        const uint32_t stg = sb + OFF_T + warp * 2048;
        const int mr = (lane & 7) + ((lane >> 3) & 1) * 8, mc = lane >> 4;
#pragma unroll
        for (int i = 0; i < 4; i++) {
          const uint32_t a = stg + mr * 128 + (((2 * i + mc) ^ (mr & 7)) << 4);
          asm volatile("stmatrix.sync.aligned.m8n8.x4.shared.b16 [%0], {%1,%2,%3,%4};" ::"r"(a), "r"(pack_bf16(sum[8 * i], sum[8 * i + 1])),
                       "r"(pack_bf16(sum[8 * i + 2], sum[8 * i + 3])), "r"(pack_bf16(sum[8 * i + 4], sum[8 * i + 5])),
                       "r"(pack_bf16(sum[8 * i + 6], sum[8 * i + 7])) : "memory");
        }
        asm volatile("fence.proxy.async.shared::cta;" ::: "memory");
        __syncwarp();
        if (elect_one()) {
          asm volatile("cp.async.bulk.tensor.3d.global.shared::cta.bulk_group [%0, {%2, %3, %4}], [%1];" ::"l"(&maps.o), "r"(stg), "r"(64 * j),
                       "r"(16 * w), "r"(2 * rb + wg) : "memory");
          asm volatile("cp.async.bulk.commit_group;\ncp.async.bulk.wait_group.read 0;" ::: "memory");
        }
      }
      if (tid == 0) { PROF_EV(15); PROF_CK(41); }
      if (tid == 128) PROF_EV(30);
    }
  } else if (warp < 12) {
    asm volatile("setmaxnreg.dec.sync.aligned.u32 104;");
    asm volatile("barrier.cluster.arrive.relaxed.aligned;" ::: "memory");
    const int t = tid - 256, w = warp - 8;
    const uint32_t ep = ld_x1(&ws->epoch[blockIdx.x * 8]);
    const uint32_t tag = (ep + 1) & 1;
    auto w_issue = [&](const CUtensorMap* m) {

      if (elect_one()) { mbar_expect_tx(bars + 8 * (B_WR + w), 3072); tma4d(sb + OFF_T + w * 3072, m, bars + 8 * (B_WR + w), 16 * kg, 0, 2 * w, tn); }

          __syncwarp();
    };
    auto gate_rows = [&] {
      const int r = 16 * j + 4 * w + (lane >> 3);
      const uint4* pg = (const uint4*)gate_w + (lane & 7);
      {
        float a = 0.f;
        asm volatile("bar.sync 4, 256;" ::: "memory");
#pragma unroll 1
        for (int hf = 0; hf < 2; hf++) {
          uint4 v[4], u[4];
#pragma unroll
          for (int kb = 0; kb < 4; kb++) v[kb] = __ldg(pg + (4 * hf + kb) * 8);
          mbar_wait(bars + 8 * (B_FE + 1 + 2 * hf), 0);
          if (hf) w_issue(&maps.wr);
#pragma unroll
          for (int kb = 0; kb < 4; kb++) u[kb] = *(const uint4*)(smem + (4 * hf + kb) * U + r * 128 + (((lane ^ r) & 7) << 4));
#pragma unroll
          for (int kb = 0; kb < 4; kb++) {
            const uint32_t uu[4] = {u[kb].x, u[kb].y, u[kb].z, u[kb].w}, vv[4] = {v[kb].x, v[kb].y, v[kb].z, v[kb].w};
#pragma unroll
            for (int e = 0; e < 4; e++) {
              uint32_t pr;
              asm("mul.rn.bf16x2 %0, %1, %2;" : "=r"(pr) : "r"(uu[e]), "r"(vv[e]));
              a += bf_lo(pr) + bf_hi(pr);
            }
          }
        }
#pragma unroll
        for (int o = 4; o; o >>= 1) a += __shfl_xor_sync(0xffffffffu, a, o);
        if ((lane & 7) == 0)
          asm volatile("st.relaxed.gpu.global.u32 [%0], %1;" ::"l"(ws->gate + rb * 128 + r),
                       "r"(pack_bf16(0.f, __fdividef(1.0f, 1.0f + __expf(-bf_lo(pack_bf16(a, 0.f))))) | tag) : "memory");
        if (t == 0) PROF_EV(18);
      }
    };
    {
      const int g = lane >> 2, q = lane & 3;
      uint32_t wf[32];
      if (!helper) {
        gate_rows();
        const uint32_t wa = sb + OFF_T + w * (3072 + 4) + q * 48 + g * 2;
#pragma unroll 1
        for (int ri = 0; ri < 2; ri++) {
          mbar_wait(bars + 8 * (B_WR + w), ri);
#pragma unroll
          for (int n2 = 0; n2 < 32 / WB; n2++) {
            uint32_t v[WB];
#pragma unroll
            for (int i = 0; i < WB; i++) {
              const int e = n2 * WB + i;
              asm volatile("ld.shared.u16 %0, [%1];" : "=r"(v[i]) : "r"(wa + ((e >> 1) & 7) * 192 + (e & 1) * (1536 + 2) + (e >> 4) * 16) : "memory");
            }
#pragma unroll
            for (int i = 0; i < WB; i++) wf[n2 * WB + i] = __byte_perm(wf[n2 * WB + i], v[i], 0x5432);
            if (WSLEEP) { asm volatile("nanosleep.u32 %0;" ::"r"(WSLEEP + (v[WB - 1] >> 16)) : "memory"); }
          }
          __syncwarp();
          if (ri == 0) w_issue(&maps.wi);
        }
        asm volatile("bar.sync 1, 128;" ::: "memory");
        if (t == 0) PROF_EV(11);
      } else {
        asm volatile("bar.sync 4, 256;" ::: "memory");
        hint_wait(&ws->cntW[0], (ep + 1) * 128u);
        const uint32_t t0 = (uint32_t)clock();
#pragma unroll 1
        for (;;) {
          uint32_t bad = 0;
#pragma unroll
          for (int i = 0; i < 32; i++) {
            const float2 v = ld_x2((const float2*)ws->Wh + (i >> 4) * 2048 + 16 * w + g + 8 * (i & 1) + 64 * q + ((i >> 1) & 7) * 256);
            wf[i] = __float_as_uint(v.x); bad |= __float_as_uint(v.y) ^ tag;
          }
          if (!__any_sync(0xffffffffu, bad & 1)) break;
          spin_guard(t0);
        }
        if (t == 0) PROF_EV(11);
      }
      if (w == 0 && elect_one()) { mbar_expect_tx(bars + 8 * B_W, 8192); bulk_load(sb + OFF_D, dtab, 8192, bars + 8 * B_W); }
      asm volatile("barrier.cluster.wait.aligned;" ::: "memory");
      mbar_wait(bars + 8 * B_W, 0);
      mbar_wait(bars + 8 * B_HX, 0);
      if (t == 0) PROF_EV(12);
      const uint32_t dd = (sb & 0x3FFFF) >> 4;
      const uint64_t dF = d128((dd + (OFF_D >> 4)) | (512u << 16)), dI = d128((dd + (OFF_D >> 4)) | (1u << 16)), dA = d128((dd + (OFF_XB >> 4)) | (512u << 16));
      float az[32];
      const int zero = blockIdx.x >> 16;
      uint32_t pf[32];
#pragma unroll
      for (int mt = 0; mt < 2; mt++) {
        wg_fence();
        if (mt == 0) mma_ss64<0, 3, 0>(az, dA, dF);
        else mma_ss64<0, 3, 2>(az, dA + 512, dF, zero);
#pragma unroll
        for (int k = 1; k < 4; k++) mma_ss64<0, 3, 1>(az, dA + (mt * 512 + k * 128), dF + k * 128);
        wg_commit();
        wg_wait<0>();
        fence_regs<0, 32>(az);
#pragma unroll
        for (int i = 0; i < 16; i++) {
          const float wr = bf_lo(wf[16 * mt + i]), wi = bf_hi(wf[16 * mt + i]);
          pf[16 * mt + i] = pack_pin(fmaf(az[2 * i], wr, -az[2 * i + 1] * wi), fmaf(az[2 * i], wi, az[2 * i + 1] * wr));
        }
      }
      if (t == 0) PROF_EV(16);
      {
        const int m = lane >> 3, r = lane & 7;
        const int sl = 2 * (m >> 1) + ((r >> 1) & 1) + 4 * (r >> 2);
        const uint32_t a0 = sb + OFF_XB + (2 * w + (m & 1)) * 2048 + sl * 64;
        uint32_t pk[16];
#pragma unroll
        for (int mt = 0; mt < 3; mt++) {
          if (mt < 2) {
            wg_fence();
            mma_rs64<0, 0, 2>(az, pf[16 * mt], pf[16 * mt + 1], pf[16 * mt + 2], pf[16 * mt + 3], dI, mt ? (int)helper : zero);
#pragma unroll
            for (int k = 1; k < 4; k++) mma_rs64<0, 0, 1>(az, pf[16 * mt + 4 * k], pf[16 * mt + 4 * k + 1], pf[16 * mt + 4 * k + 2], pf[16 * mt + 4 * k + 3], dI + k * 2);
            wg_commit();
          }
          if (mt > 0 && !helper) {
#pragma unroll
            for (int i = 0; i < 4; i++) stsm4t(a0 + ((((mt - 1) * 2 + (r & 1)) ^ (sl >> 1)) << 4) + i * 512, pk[4 * i], pk[4 * i + 1], pk[4 * i + 2], pk[4 * i + 3]);
          }
          if (mt < 2) {
            wg_wait<0>();
            fence_regs<0, 32>(az);
#pragma unroll
            for (int i = 0; i < 16; i++) pk[i] = pack_pin(az[2 * i], az[2 * i + 1]);
          }
        }
      }
      if (helper) {
#pragma unroll
        for (int i = 0; i < 16; i++) {
          const int n = i >> 1, s0 = 8 * (n >> 1) + 2 * (n & 1) + (q & 1) + 4 * (q >> 1);
          if ((n & 1) == (int)(blockIdx.x & 1)) st_u2(ws->Ts + s0 * 64 + 16 * w + g + 8 * (i & 1), pack_bf16(az[2 * i], az[2 * i + 1]), tag);
        }
        __syncwarp();
        hint_add_if(lane == 0, &ws->cntH[0]);
        if (t == 0) { ws->epoch[blockIdx.x * 8] = ep + 1; PROF_EV(13); }
      } else {
        asm volatile("fence.proxy.async.shared::cta;" ::: "memory");
        __syncwarp();
        if (elect_one()) {
          if (t == 0) PROF_EV(17);
          if (SPACE) __nanosleep(SPACE * w);
          asm volatile("cp.async.bulk.tensor.3d.global.shared::cta.bulk_group [%0, {%2, %3, %4}], [%1];" ::"l"(&maps.ts), "r"(sb + OFF_XB + w * 4096),
                       "r"(32 * kg), "r"(0), "r"(8 * tn + 2 * w) : "memory");
          bulk_done_signal(&ws->cntT[32 * j]);
          asm volatile("mbarrier.arrive.shared::cluster.b64 _, [%0];" ::"r"(mapa(bars + 8 * B_RD0, rank ^ 1)) : "memory");
          if (t == 96) PROF_EV(13);
        }
        __syncwarp();
        if (j == 0) {
          hint_wait(&ws->cntH[0], (ep + 1) * 8u);
          const uint32_t t0 = (uint32_t)clock();
          float2 v;
          do { v = ld_x2((const float2*)ws->Ts + 2 * rb * 64 + t); spin_guard(t0); } while (__any_sync(0xffffffffu, (__float_as_uint(v.y) ^ tag) & 1));
          mbar_wait(bars + 8 * B_TL, 0);
          const uint32_t u = __float_as_uint(v.x);
          *(uint16_t*)(smem + OFF_T + t * 128 + ((t & 7) << 4)) = (uint16_t)u;
          *(uint16_t*)(smem + OFF_T + t * 128 + (((t & 7) ^ 1) << 4)) = (uint16_t)(u >> 16);
          asm volatile("fence.proxy.async.shared::cta;" ::: "memory");
          __syncwarp();
          mbar_arrive_if(lane == 0, bars + 8 * B_T);
        }
      }
    }
  } else {
    asm volatile("setmaxnreg.dec.sync.aligned.u32 24;");
    auto xf_load = [&](int q) {
      const uint32_t fb = bars + 8 * (B_FX + q);
      mbar_expect_tx(fb, U + 8192);
      tma3d(sb + q * U, &maps.x, fb, 64 * q, 0, 2 * rb);
      if (q >= 4) mbar_wait(bars + 8 * (B_FE + ((q - 4) >> 1)), 0);
      tma2d(sb + OFF_XB + (q & 3) * 8192, &maps.ft, fb, 64 * q, 64 * j);
    };
    if (elect_one()) {
      if (warp == 14) {
#pragma unroll
        for (int i = 0; i < B_FT; i++) mbar_init(bars + 8 * i, 1);
        asm volatile("fence.mbarrier_init.release.cluster;" ::: "memory");
        if (!helper) {
#pragma unroll 1
          for (int n = 0; n < 2; n++) {
            const uint32_t fb = bars + 8 * (B_FA + n);
            xf_load(2 * n); xf_load(2 * n + 1);
            mbar_expect_tx(fb, U);
            tma2d(sb + OFF_RING + n * U, &maps.g64, fb, f_full, 64 * n);
            tma2d(sb + OFF_RING + n * U + 8192, &maps.u64, fb, f_full, 64 * n);
          }
        }
      } else if (warp == 15) {
#pragma unroll
        for (int i = B_FT; i < NBAR; i++) mbar_init(bars + 8 * i, i < B_EA ? 1 : i < B_T ? 2 : 4);
#pragma unroll
        for (int i = 0; i < 8; i++) mbar_expect_tx(bars + 8 * (B_Z + i), U / 2);
        asm volatile("fence.mbarrier_init.release.cluster;" ::: "memory");
        asm volatile("fence.proxy.async.shared::cta;" ::: "memory");
      }
    }
    __syncwarp();
    asm volatile("bar.arrive 0, 384;" ::: "memory");
    asm volatile("bar.arrive 4, 256;" ::: "memory");
    __syncwarp();
    asm volatile("barrier.cluster.arrive.relaxed.aligned;" ::: "memory");
    asm volatile("bar.sync 3, 128;" ::: "memory");
    if (warp == 15 && !helper) {
        mbar_wait(bars + 8 * B_FE, 0);
        const uint32_t tag = (ld_x1(&ws->epoch[blockIdx.x * 8]) + 1) & 1;
        const int c = lane >> 4, jj = 16 * blockIdx.x + (lane & 15), jm = (2048 - jj) & 2047;
        const unsigned short* pr = (const unsigned short*)w_r + 256 * c;
        const unsigned short* pi = (const unsigned short*)w_i + 256 * c;
        const float wr = 0.25f * (bf_lo(__ldg(pr + jj * 257)) + bf_lo(__ldg(pr + jm * 257)));
        const float wi = 0.25f * (bf_lo(__ldg(pi + jj * 257)) - bf_lo(__ldg(pi + jm * 257)));
        st_u2(ws->Wh + c * 2048 + jj, c ? pack_bf16(-wi, wr) : pack_bf16(wr, wi), tag);
        __syncwarp();
        hint_add_if(lane == 0, &ws->cntW[0]);
        mbar_wait(bars + 8 * B_XS, 0);
        const uint32_t t0 = (uint32_t)clock();
        uint4 v;
        do { v = ld_x4(ws->gate + rb * 128 + 4 * lane); spin_guard(t0); } while (__any_sync(0xffffffffu, ((v.x ^ tag) | (v.y ^ tag) | (v.z ^ tag) | (v.w ^ tag)) & 1));
        *(uint4*)(smem + OFF_G + lane * 16) = v;
        __syncwarp();
        mbar_arrive_if(lane < 4, bars + 8 * B_G);
      }
    if ((!helper || warp == 15) && elect_one()) {
      if (warp < 14) {
        const int p = warp - 12;
#pragma unroll 1
        for (int i = 4 + p; i < 14; i += 2) asm volatile("prefetch.tensormap [%0];" ::"l"((const char*)&maps + i * 128) : "memory");
#pragma unroll 1
        for (int n = 2; n < 31; n++) {
          const bool table = n == 4 || n >= 29;
          const bool half = n >= 17 && n < 21;
          const int q = n < 4 ? n : n < 17 ? n - 1 : n - 5;
          const CUtensorMap* m = table ? &maps.e : half ? &maps.g32 + p : &maps.g64 + p;
          const int c0 = table ? 0 : half ? f_half : f_full + 64 * (q >> 3);
          const int c1 = table ? (2 * rb + ((n & 1) ^ 1)) * 128 + 64 * p : half ? 128 * (n - 17) : 64 * (q & 7);
          const uint32_t fb = bars + 8 * (B_FA + (n & 3)), dst = sb + OFF_RING + (n & 3) * U + p * 8192;
          if (n < 4) mbar_wait(bars + 8 * (B_FE + n - 2), 0);
          else mbar_wait(bars + 8 * (B_EA + (n & 3)), ((n >> 2) & 1) ^ 1);
          tma2d(dst, m, fb, c0, c1);
          if (p == 0) mbar_expect_tx(fb, U);
        }
      } else if (warp == 15) {
        const unsigned ep1 = ld_x1(&ws->epoch[blockIdx.x * 8]) + 1;
        flag_wait(&ws->cntX[helper ? 0 : 32 * j], ep1 * 16u);
        PROF_EV(22);
        mbar_expect_tx(bars + 8 * B_HX, U);
        bulk_load(sb + OFF_XB, ws->X + (size_t)(helper ? 128 : kg * 8 + tn) * 8192, U, bars + 8 * B_HX);
        if (!helper) {
          flag_wait(&ws->cntT[32 * j], ep1 * 64u);
          PROF_EV(23);
          mbar_expect_tx(bars + 8 * B_TL, U);
          tma3d(sb + OFF_T, &maps.t, bars + 8 * B_TL, 64 * j, 0, 2 * rb);
#pragma unroll 1
          for (int i = 0; i < 3; i++) {
            flag_wait(&ws->cntP[32 * (rb * 8 + j) + i], ep1 * 8u);
            mbar_wait(bars + 8 * (B_PZ + (i == 0)), 0);
            if (i == 2) PROF_EV(26);
            mbar_expect_tx(bars + 8 * (B_HP + i), U);
            bulk_load(sb + (i ? (i - 1) * U : OFF_T), ws->part + (size_t)((rb * 8 + j) * 3 + i) * 1024, U, bars + 8 * (B_HP + i));
          }
          ws->epoch[blockIdx.x * 8] = ep1;
        }
      } else {
#pragma unroll 1
        for (int q = 4; q < 8; q++) xf_load(q);
        mbar_wait(bars + 8 * (B_FE + 2), 0);
        mbar_expect_tx(bars + 8 * B_E0, U);
        tma2d(sb + OFF_XB, &maps.e, bars + 8 * B_E0, 0, 2 * rb * 128);
        tma2d(sb + OFF_XB + 8192, &maps.e, bars + 8 * B_E0, 0, 2 * rb * 128 + 64);
#pragma unroll 1
        for (int h2 = 0; h2 < 2; h2++) {
          const int s0 = 2 * rb + h2, sg = (s0 & ~6) | ((s0 & 2) << 1) | ((s0 & 4) >> 1);
          mbar_wait(bars + 8 * (B_XS + h2), 0);
#pragma unroll 1
          for (int c = 0; c < 2; c++) {
            asm volatile("cp.async.bulk.tensor.4d.global.shared::cta.bulk_group [%0, {%2, %3, %4, %5}], [%1];" ::"l"(&maps.xs),
                         "r"(sb + OFF_XB + h2 * 8192 + c * 4096), "r"(0), "r"(sg), "r"(0), "r"(16 * j + 8 * c) : "memory");
            if (j == 0)
              asm volatile("cp.async.bulk.global.shared::cta.bulk_group [%0], [%1], 256;" ::"l"(ws->X + 128 * 8192 + c * 4096 + sg * 128),
                           "r"(sb + OFF_SP + h2 * 512 + c * 256) : "memory");
            if (SPACE && h2 + c < 2) __nanosleep(SPACE);
          }
        }
        bulk_done_signal(&ws->cntX[32 * j]);
        PROF_EV(20);
        if (rb < 8) asm volatile("cp.async.bulk.prefetch.tensor.2d.L2.global [%0, {%1, %2}];" ::"l"(&maps.g32 + (rb >> 2)), "r"(f_half), "r"(128 * (rb & 3)) : "memory");
        else asm volatile("cp.async.bulk.prefetch.tensor.2d.L2.global [%0, {%1, %2}];" ::"l"(&maps.d224), "r"(64 * (rb - 8)), "r"(224 * j) : "memory");
#pragma unroll 1
        for (int t = 0; t < 8; t++) {
          const int i = t < 3 ? t + 1 : t < 6 ? t - 2 : 0;
          const int col = 64 * (2 * ((q4 + i) & 3) + ((t < 3 || t == 6) ? 1 - rank : rank));
          const uint32_t fb = bars + 8 * (B_FT + (t & 3)), dst = sb + (t & 3) * TB;
          mbar_wait(bars + 8 * (B_ET + (t == 2 ? 3 : t & 3)), t >> 2);
          mbar_expect_tx(fb, TB);
          tma2d(dst, &maps.d224, fb, col, 224 * j);
          if (t < 2) mbar_wait(bars + 8 * (B_ET + t + 1), 0);
          tma2d(dst + 28672, &maps.ft, fb, col, 64 * j);
        }
      }
    }
  }
}

typedef CUresult (*EncodeFn)(CUtensorMap*, CUtensorMapDataType, cuuint32_t, void*, const cuuint64_t*, const cuuint64_t*, const cuuint32_t*,
                             const cuuint32_t*, CUtensorMapInterleave, CUtensorMapSwizzle, CUtensorMapL2promotion, CUtensorMapFloatOOBfill);

static void encode(EncodeFn f, CUtensorMap* m, const void* base, int rank, const cuuint64_t* dims, const cuuint64_t* strides, const cuuint32_t* box,
                   CUtensorMapSwizzle sw) {
  cuuint32_t es[5] = {1, 1, 1, 1, 1};
  f(m, CU_TENSOR_MAP_DATA_TYPE_BFLOAT16, rank, (void*)base, dims, strides, box, es, CU_TENSOR_MAP_INTERLEAVE_NONE, sw,
    CU_TENSOR_MAP_L2_PROMOTION_L2_128B, CU_TENSOR_MAP_FLOAT_OOB_FILL_NONE);
}

extern "C" void kernel_launch(void* const* d_in, const int* in_sizes, int n_in, void* d_out, int out_size) {
  (void)in_sizes; (void)n_in; (void)out_size;
  const __nv_bfloat16* x = (const __nv_bfloat16*)d_in[0];
  const __nv_bfloat16* w_r = (const __nv_bfloat16*)d_in[1];
  const __nv_bfloat16* w_i = (const __nv_bfloat16*)d_in[2];
  const __nv_bfloat16* Wg = (const __nv_bfloat16*)d_in[4];
  const __nv_bfloat16* Wu = (const __nv_bfloat16*)d_in[5];
  const __nv_bfloat16* Wd = (const __nv_bfloat16*)d_in[6];
  const __nv_bfloat16* gw = (const __nv_bfloat16*)d_in[7];

  void* fp = nullptr; cudaDriverEntryPointQueryResult qr;
  cudaGetDriverEntryPoint("cuTensorMapEncodeTiled", &fp, cudaEnableDefault, &qr);
  EncodeFn enc = (EncodeFn)fp;
  void *pFT, *pET, *pDT, *pW;
  cudaGetSymbolAddress(&pDT, g_DT); cudaGetSymbolAddress(&pW, g_work);
  void *pX = ((Work*)pW)->X, *pT = ((Work*)pW)->T;
  cudaGetSymbolAddress(&pFT, g_FT); cudaGetSymbolAddress(&pET, g_ET);

  Maps mp;
  const CUtensorMapSwizzle S128 = CU_TENSOR_MAP_SWIZZLE_128B, S64 = CU_TENSOR_MAP_SWIZZLE_64B;
  { cuuint64_t d[3] = {512, 64, 32}, s[2] = {32768, 1024}; cuuint32_t b[3] = {64, 64, 2}, b2[3] = {64, 16, 1};
    encode(enc, &mp.x, x, 3, d, s, b, S128); encode(enc, &mp.o, d_out, 3, d, s, b2, S128); }
  { cuuint64_t d[2] = {512, 512}, s[1] = {1024}; cuuint32_t b[2] = {64, 64}; encode(enc, &mp.ft, pFT, 2, d, s, b, S128); }
  { cuuint64_t d[4] = {128, 32, 2, 129}, s[3] = {256, 8192, 16384}; cuuint32_t b[4] = {128, 1, 2, 8}; encode(enc, &mp.xs, pX, 4, d, s, b, CU_TENSOR_MAP_SWIZZLE_NONE); }
  { cuuint64_t d[3] = {512, 32, 64}, s[2] = {65536, 1024}; cuuint32_t b[3] = {32, 32, 2}; encode(enc, &mp.ts, pT, 3, d, s, b, S64); }
  { cuuint64_t d[3] = {512, 64, 32}, s[2] = {1024, 65536}; cuuint32_t b[3] = {64, 64, 2}; encode(enc, &mp.t, pT, 3, d, s, b, S128); }
  { cuuint64_t d[2] = {64, 4096}, s[1] = {128}; cuuint32_t b[2] = {64, 64}; encode(enc, &mp.e, pET, 2, d, s, b, S128); }
  { cuuint64_t d[2] = {1792, 512}, s[1] = {3584}; cuuint32_t b[2] = {64, 64}, b2[2] = {32, 128};
    encode(enc, &mp.g64, Wg, 2, d, s, b, S128); encode(enc, &mp.u64, Wu, 2, d, s, b, S128);
    encode(enc, &mp.g32, Wg, 2, d, s, b2, S64); encode(enc, &mp.u32, Wu, 2, d, s, b2, S64); }
  { cuuint64_t d[2] = {512, 1792}, s[1] = {1024}; cuuint32_t b[2] = {64, 224}; encode(enc, &mp.d224, Wd, 2, d, s, b, S128); }
  { cuuint64_t d[4] = {264, 32, 8, 8}, s[3] = {32896, 512, 4112}; cuuint32_t b[4] = {24, 32, 2, 1};
    encode(enc, &mp.wr, w_r, 4, d, s, b, CU_TENSOR_MAP_SWIZZLE_NONE); encode(enc, &mp.wi, w_i, 4, d, s, b, CU_TENSOR_MAP_SWIZZLE_NONE); }

  cudaFuncSetAttribute(fused_kernel, cudaFuncAttributeMaxDynamicSharedMemorySize, SMEM_BYTES);
  fused_kernel<<<NCTA, 512, SMEM_BYTES>>>((Work*)pW, (const uint16_t*)pDT, w_r, w_i, gw, x, mp);
}
```

```cpp
#include <cuda_runtime.h>
#include <cuda_bf16.h>
#include <cuda.h>
#include <stdint.h>

namespace tbl {
constexpr double PI = 3.14159265358979323846264338327950288;
constexpr double sin_s(double x) { double t = x, s = x; for (int n = 1; n < 12; n++) { t *= -x * x / ((2 * n) * (2 * n + 1)); s += t; } return s; }
constexpr double cos_s(double x) { double t = 1, s = 1; for (int n = 1; n < 12; n++) { t *= -x * x / ((2 * n - 1) * (2 * n)); s += t; } return s; }
constexpr double cos2048(int m) {
  m &= 2047; if (m > 1024) m = 2048 - m;
  bool neg = false; if (m > 512) { m = 1024 - m; neg = true; }
  double v = (m <= 256) ? cos_s(2 * PI * m / 2048) : sin_s(2 * PI * (512 - m) / 2048);
  return neg ? -v : v;
}
constexpr uint16_t to_bf16(double v) {
  if (v == 0) return 0;
  uint16_t s = 0; if (v < 0) { s = 0x8000; v = -v; }
  int e = 0; while (v >= 2) { v /= 2; e++; } while (v < 1) { v *= 2; e--; }
  double m = (v - 1) * 128; int mi = (int)m; double fr = m - mi;
  if (fr > 0.5 || (fr == 0.5 && (mi & 1))) mi++;
  if (mi == 128) { mi = 0; e++; }
  return (uint16_t)(s | ((e + 127) << 7) | mi);
}
struct CosT { uint16_t v[2048]; constexpr CosT() : v() { for (int i = 0; i < 2048; i++) v[i] = to_bf16(cos2048(i)); } };
struct alignas(1024) FT {
  uint16_t v[512 * 512];
  constexpr FT() : v() {
    CosT c;
    for (int r = 0; r < 512; r++) {
      int k = (r >> 4) * 8 + (r & 7), e = (r >> 3) & 1;
      int mul = 4 * k, add = e ? 512 : 0;
      if (k == 0 && e == 1) { mul = 1024; add = 0; }
      for (int d = 0; d < 512; d++) v[r * 512 + d] = c.v[(d * mul + add) & 2047];
    }
  }
};
struct alignas(1024) ET {
  uint16_t v[2048 * 128];
  constexpr ET() : v() {
    CosT c;
    for (int s = 0; s < 2048; s++)
      for (int j = 0; j < 64; j++) {
        const int o = (s & 31) * 8192 + (s >> 5) * 64 + j;
        v[o] = c.v[(s * j) & 2047]; v[o + 4096] = c.v[(s * j + 512) & 2047];
      }
  }
};
struct alignas(1024) DT {
  uint16_t v[64 * 64];
  constexpr DT() : v() {
    CosT c;
    for (int r = 0; r < 64; r++)
      for (int n = 0; n < 64; n++) {
        const int sg = r >> 1, s0 = (sg & ~6) | ((sg & 2) << 1) | ((sg & 4) >> 1), e = r & 1, f = n & 1;
        const int m = 64 * s0 * (n >> 1) + (e == f ? 0 : e ? -512 : 512);
        v[r * 64 + (((n >> 3) ^ (r & 7)) << 3) + (n & 7)] = c.v[m & 2047];
      }
  }
};
}

__device__ constexpr tbl::FT g_FT = tbl::FT();
__device__ constexpr tbl::ET g_ET = tbl::ET();
__device__ constexpr tbl::DT g_DT = tbl::DT();

struct alignas(1024) Work {
  unsigned epoch[132 * 8];
  unsigned cntX[8 * 32], cntT[8 * 32], cntP[128 * 32], cntW[32], cntH[32];
  alignas(16) float gate[16 * 128];
  alignas(16) uint2 Wh[2 * 2048];
  alignas(16) uint2 Ts[32 * 64];
  alignas(1024) uint16_t X[129 * 8192];
  alignas(1024) uint16_t T[32 * 64 * 512];
  alignas(1024) uint4 part[128 * 3 * 1024];
};
__device__ Work g_work;
#define PROF_EV(i) do {} while (0)
#define PROF_CK(i) do {} while (0)

__device__ __forceinline__ uint32_t smem_u32(const void* p) { return (uint32_t)__cvta_generic_to_shared(p); }
__device__ __forceinline__ void mbar_init(uint32_t bar, uint32_t cnt) { asm volatile("mbarrier.init.shared::cta.b64 [%0], %1;" ::"r"(bar), "r"(cnt)); }
__device__ __forceinline__ void mbar_expect_tx(uint32_t bar, uint32_t bytes) { asm volatile("mbarrier.arrive.expect_tx.shared::cta.b64 _, [%0], %1;" ::"r"(bar), "r"(bytes) : "memory"); }
__device__ __forceinline__ void mbar_arrive(uint32_t bar) { asm volatile("mbarrier.arrive.shared::cta.b64 _, [%0];" ::"r"(bar) : "memory"); }
__device__ __forceinline__ bool elect_one() {
  uint32_t p;
  asm volatile("{\n.reg .pred p;\nelect.sync _|p, 0xffffffff;\nselp.u32 %0, 1, 0, p;\n}" : "=r"(p));
  return p;
}
__device__ __forceinline__ void mbar_arrive_if(bool p, uint32_t bar) {
  asm volatile("{\n.reg .pred p;\nsetp.ne.b32 p, %1, 0;\n@p mbarrier.arrive.shared::cta.b64 _, [%0];\n}" ::"r"(bar), "r"((int)p) : "memory");
}
__device__ __forceinline__ void hint_add_if(bool p, unsigned* a) {
  asm volatile("{\n.reg .pred p;\nsetp.ne.b32 p, %1, 0;\n@p red.relaxed.gpu.global.add.u32 [%0], 1;\n}" ::"l"(a), "r"((int)p) : "memory");
}
__device__ __forceinline__ bool mbar_try(uint32_t bar, uint32_t parity) {
  uint32_t ok;
  asm volatile("{\n.reg .pred p;\nmbarrier.test_wait.parity.shared::cta.b64 p, [%1], %2;\nselp.u32 %0, 1, 0, p;\n}" : "=r"(ok) : "r"(bar), "r"(parity) : "memory");
  return ok;
}
__device__ __forceinline__ void mbar_wait(uint32_t bar, uint32_t parity) {
  asm volatile(
      "{\n.reg .pred p;\n.reg .u32 n;\nmov.u32 n, 0;\n"
      "W_LOOP:\nmbarrier.try_wait.parity.shared::cta.b64 p, [%0], %1;\n@p bra W_DONE;\n"
      "add.u32 n, n, 1;\nsetp.lt.u32 p, n, 0x40000;\n@p bra W_LOOP;\ntrap;\nW_DONE:\n}" ::"r"(bar), "r"(parity) : "memory");
}
__device__ __forceinline__ void bulk_load(uint32_t dst, const void* src, uint32_t bytes, uint32_t bar) {
  asm volatile("cp.async.bulk.shared::cluster.global.mbarrier::complete_tx::bytes [%0], [%1], %2, [%3];" ::"r"(dst), "l"(src), "r"(bytes), "r"(bar) : "memory");
}
__device__ __forceinline__ void spin_guard(uint32_t t0) { if ((uint32_t)clock() - t0 > (1u << 30)) __trap(); }
__device__ __forceinline__ float2 ld_x2(const float2* p) { float2 v; asm volatile("ld.relaxed.gpu.global.v2.f32 {%0,%1}, [%2];" : "=f"(v.x), "=f"(v.y) : "l"(p) : "memory"); return v; }
__device__ __forceinline__ void st_u2(uint2* p, uint32_t a, uint32_t b) { asm volatile("st.relaxed.gpu.global.v2.u32 [%0], {%1,%2};" ::"l"(p), "r"(a), "r"(b) : "memory"); }
__device__ __forceinline__ uint32_t ld_x1(const void* p) { uint32_t v; asm volatile("ld.relaxed.gpu.global.u32 %0, [%1];" : "=r"(v) : "l"(p) : "memory"); return v; }
__device__ __forceinline__ uint4 ld_x4(const void* p) { uint4 v; asm volatile("ld.relaxed.gpu.global.v4.u32 {%0,%1,%2,%3}, [%4];" : "=r"(v.x), "=r"(v.y), "=r"(v.z), "=r"(v.w) : "l"(p) : "memory"); return v; }
__device__ __forceinline__ uint32_t mapa(uint32_t a, uint32_t cta) { uint32_t r; asm volatile("mapa.shared::cluster.u32 %0, %1, %2;" : "=r"(r) : "r"(a), "r"(cta)); return r; }
__device__ __forceinline__ void stsm4t(uint32_t a, uint32_t r0, uint32_t r1, uint32_t r2, uint32_t r3) {
  asm volatile("stmatrix.sync.aligned.m8n8.x4.trans.shared.b16 [%0], {%1,%2,%3,%4};" ::"r"(a), "r"(r0), "r"(r1), "r"(r2), "r"(r3) : "memory");
}
__device__ __forceinline__ void hint_add(unsigned* p) { asm volatile("red.relaxed.gpu.global.add.u32 [%0], 1;" ::"l"(p) : "memory"); }
__device__ __forceinline__ void hint_wait(const unsigned* p, unsigned target) {
  const uint32_t t0 = (uint32_t)clock();
  while ((int)(ld_x1(p) - target) < 0) spin_guard(t0);
}
__device__ __forceinline__ void bulk_done_signal(unsigned* p) {
  asm volatile("cp.async.bulk.commit_group;\ncp.async.bulk.wait_group 0;\nfence.proxy.async.global;" ::: "memory");
  hint_add(p);
}
__device__ __forceinline__ void flag_wait(const unsigned* p, unsigned target) {
  hint_wait(p, target);
  asm volatile("fence.proxy.async.global;" ::: "memory");
}
__device__ __forceinline__ void tma2d(uint32_t dst, const CUtensorMap* m, uint32_t bar, int c0, int c1) {
  asm volatile("cp.async.bulk.tensor.2d.shared::cluster.global.mbarrier::complete_tx::bytes [%0], [%1, {%3, %4}], [%2];" ::"r"(dst), "l"(m), "r"(bar), "r"(c0), "r"(c1) : "memory");
}
__device__ __forceinline__ void tma3d(uint32_t dst, const CUtensorMap* m, uint32_t bar, int c0, int c1, int c2) {
  asm volatile("cp.async.bulk.tensor.3d.shared::cluster.global.mbarrier::complete_tx::bytes [%0], [%1, {%3, %4, %5}], [%2];" ::"r"(dst), "l"(m), "r"(bar), "r"(c0), "r"(c1), "r"(c2) : "memory");
}
__device__ __forceinline__ void tma4d(uint32_t dst, const CUtensorMap* m, uint32_t bar, int c0, int c1, int c2, int c3) {
  asm volatile("cp.async.bulk.tensor.4d.shared::cluster.global.mbarrier::complete_tx::bytes [%0], [%1, {%3, %4, %5, %6}], [%2];" ::"r"(dst), "l"(m), "r"(bar), "r"(c0), "r"(c1), "r"(c2), "r"(c3) : "memory");
}
__device__ __forceinline__ void wg_fence() { asm volatile("wgmma.fence.sync.aligned;" ::: "memory"); }
__device__ __forceinline__ void wg_commit() { asm volatile("wgmma.commit_group.sync.aligned;" ::: "memory"); }
template <int N> __device__ __forceinline__ void wg_wait() { asm volatile("wgmma.wait_group.sync.aligned %0;" ::"n"(N) : "memory"); }
template <int O, int N, int NN> __device__ __forceinline__ void fence_regs(float (&d)[NN]) {
#pragma unroll
  for (int i = 0; i < N; i++) asm volatile("" : "+f"(d[O + i])::"memory");
}
__device__ __forceinline__ uint32_t pack_bf16(float lo, float hi) {
  uint32_t r; asm("cvt.rn.bf16x2.f32 %0, %1, %2;" : "=r"(r) : "f"(hi), "f"(lo)); return r;
}
__device__ __forceinline__ uint32_t pack_pin(float lo, float hi) {
  uint32_t r; asm volatile("cvt.rn.bf16x2.f32 %0, %1, %2;" : "=r"(r) : "f"(hi), "f"(lo) : "memory"); return r;
}
__device__ __forceinline__ uint32_t add_bf2(uint32_t a, uint32_t b) { uint32_t r; asm("add.rn.bf16x2 %0, %1, %2;" : "=r"(r) : "r"(a), "r"(b)); return r; }
__device__ __forceinline__ float bf_lo(uint32_t u) { return __uint_as_float(u << 16); }
__device__ __forceinline__ float bf_hi(uint32_t u) { return __uint_as_float(u & 0xffff0000u); }

__device__ __forceinline__ uint64_t d128(uint32_t lo) { uint64_t d; asm("mov.b64 %0, {%1, 0x40000040};" : "=l"(d) : "r"(lo)); return d; }
__device__ __forceinline__ uint64_t d64(uint32_t lo) { uint64_t d; asm("mov.b64 %0, {%1, 0x80000020};" : "=l"(d) : "r"(lo)); return d; }
template<int O,int TB,int ACC,int NN> __device__ __forceinline__ void mma_ss64(float (&d)[NN], uint64_t da, uint64_t db, int sd = 0){
  if constexpr (ACC == 1) asm volatile("wgmma.mma_async.sync.aligned.m64n64k16.f32.bf16.bf16 {%0,%1,%2,%3,%4,%5,%6,%7,%8,%9,%10,%11,%12,%13,%14,%15,%16,%17,%18,%19,%20,%21,%22,%23,%24,%25,%26,%27,%28,%29,%30,%31}, %32, %33, 1, 1, 1, %35, %34;"
   : "+f"(d[O+0]), "+f"(d[O+1]), "+f"(d[O+2]), "+f"(d[O+3]), "+f"(d[O+4]), "+f"(d[O+5]), "+f"(d[O+6]), "+f"(d[O+7]), "+f"(d[O+8]), "+f"(d[O+9]), "+f"(d[O+10]), "+f"(d[O+11]), "+f"(d[O+12]), "+f"(d[O+13]), "+f"(d[O+14]), "+f"(d[O+15]), "+f"(d[O+16]), "+f"(d[O+17]), "+f"(d[O+18]), "+f"(d[O+19]), "+f"(d[O+20]), "+f"(d[O+21]), "+f"(d[O+22]), "+f"(d[O+23]), "+f"(d[O+24]), "+f"(d[O+25]), "+f"(d[O+26]), "+f"(d[O+27]), "+f"(d[O+28]), "+f"(d[O+29]), "+f"(d[O+30]), "+f"(d[O+31])
   : "l"(da), "l"(db), "n"(TB & 1), "n"(TB >> 1));
  else if constexpr (ACC == 0) asm volatile("wgmma.mma_async.sync.aligned.m64n64k16.f32.bf16.bf16 {%0,%1,%2,%3,%4,%5,%6,%7,%8,%9,%10,%11,%12,%13,%14,%15,%16,%17,%18,%19,%20,%21,%22,%23,%24,%25,%26,%27,%28,%29,%30,%31}, %32, %33, 0, 1, 1, %35, %34;"
   : "=f"(d[O+0]), "=f"(d[O+1]), "=f"(d[O+2]), "=f"(d[O+3]), "=f"(d[O+4]), "=f"(d[O+5]), "=f"(d[O+6]), "=f"(d[O+7]), "=f"(d[O+8]), "=f"(d[O+9]), "=f"(d[O+10]), "=f"(d[O+11]), "=f"(d[O+12]), "=f"(d[O+13]), "=f"(d[O+14]), "=f"(d[O+15]), "=f"(d[O+16]), "=f"(d[O+17]), "=f"(d[O+18]), "=f"(d[O+19]), "=f"(d[O+20]), "=f"(d[O+21]), "=f"(d[O+22]), "=f"(d[O+23]), "=f"(d[O+24]), "=f"(d[O+25]), "=f"(d[O+26]), "=f"(d[O+27]), "=f"(d[O+28]), "=f"(d[O+29]), "=f"(d[O+30]), "=f"(d[O+31])
   : "l"(da), "l"(db), "n"(TB & 1), "n"(TB >> 1));
  else asm volatile("{\n.reg .pred p;\nsetp.ne.b32 p, %36, 0;\nwgmma.mma_async.sync.aligned.m64n64k16.f32.bf16.bf16 {%0,%1,%2,%3,%4,%5,%6,%7,%8,%9,%10,%11,%12,%13,%14,%15,%16,%17,%18,%19,%20,%21,%22,%23,%24,%25,%26,%27,%28,%29,%30,%31}, %32, %33, p, 1, 1, %35, %34;\n}"
   : "+f"(d[O+0]), "+f"(d[O+1]), "+f"(d[O+2]), "+f"(d[O+3]), "+f"(d[O+4]), "+f"(d[O+5]), "+f"(d[O+6]), "+f"(d[O+7]), "+f"(d[O+8]), "+f"(d[O+9]), "+f"(d[O+10]), "+f"(d[O+11]), "+f"(d[O+12]), "+f"(d[O+13]), "+f"(d[O+14]), "+f"(d[O+15]), "+f"(d[O+16]), "+f"(d[O+17]), "+f"(d[O+18]), "+f"(d[O+19]), "+f"(d[O+20]), "+f"(d[O+21]), "+f"(d[O+22]), "+f"(d[O+23]), "+f"(d[O+24]), "+f"(d[O+25]), "+f"(d[O+26]), "+f"(d[O+27]), "+f"(d[O+28]), "+f"(d[O+29]), "+f"(d[O+30]), "+f"(d[O+31])
   : "l"(da), "l"(db), "n"(TB & 1), "n"(TB >> 1), "r"(sd));
}
template<int O,int TB,int ACC,int NN> __device__ __forceinline__ void mma_rs64(float (&d)[NN], uint32_t a0, uint32_t a1, uint32_t a2, uint32_t a3, uint64_t db, int sd = 0){
  if constexpr (ACC == 1) asm volatile("wgmma.mma_async.sync.aligned.m64n64k16.f32.bf16.bf16 {%0,%1,%2,%3,%4,%5,%6,%7,%8,%9,%10,%11,%12,%13,%14,%15,%16,%17,%18,%19,%20,%21,%22,%23,%24,%25,%26,%27,%28,%29,%30,%31}, {%32,%33,%34,%35}, %36, 1, 1, 1, %37;"
   : "+f"(d[O+0]), "+f"(d[O+1]), "+f"(d[O+2]), "+f"(d[O+3]), "+f"(d[O+4]), "+f"(d[O+5]), "+f"(d[O+6]), "+f"(d[O+7]), "+f"(d[O+8]), "+f"(d[O+9]), "+f"(d[O+10]), "+f"(d[O+11]), "+f"(d[O+12]), "+f"(d[O+13]), "+f"(d[O+14]), "+f"(d[O+15]), "+f"(d[O+16]), "+f"(d[O+17]), "+f"(d[O+18]), "+f"(d[O+19]), "+f"(d[O+20]), "+f"(d[O+21]), "+f"(d[O+22]), "+f"(d[O+23]), "+f"(d[O+24]), "+f"(d[O+25]), "+f"(d[O+26]), "+f"(d[O+27]), "+f"(d[O+28]), "+f"(d[O+29]), "+f"(d[O+30]), "+f"(d[O+31])
   : "r"(a0), "r"(a1), "r"(a2), "r"(a3), "l"(db), "n"(TB));
  else if constexpr (ACC == 0) asm volatile("wgmma.mma_async.sync.aligned.m64n64k16.f32.bf16.bf16 {%0,%1,%2,%3,%4,%5,%6,%7,%8,%9,%10,%11,%12,%13,%14,%15,%16,%17,%18,%19,%20,%21,%22,%23,%24,%25,%26,%27,%28,%29,%30,%31}, {%32,%33,%34,%35}, %36, 0, 1, 1, %37;"
   : "=f"(d[O+0]), "=f"(d[O+1]), "=f"(d[O+2]), "=f"(d[O+3]), "=f"(d[O+4]), "=f"(d[O+5]), "=f"(d[O+6]), "=f"(d[O+7]), "=f"(d[O+8]), "=f"(d[O+9]), "=f"(d[O+10]), "=f"(d[O+11]), "=f"(d[O+12]), "=f"(d[O+13]), "=f"(d[O+14]), "=f"(d[O+15]), "=f"(d[O+16]), "=f"(d[O+17]), "=f"(d[O+18]), "=f"(d[O+19]), "=f"(d[O+20]), "=f"(d[O+21]), "=f"(d[O+22]), "=f"(d[O+23]), "=f"(d[O+24]), "=f"(d[O+25]), "=f"(d[O+26]), "=f"(d[O+27]), "=f"(d[O+28]), "=f"(d[O+29]), "=f"(d[O+30]), "=f"(d[O+31])
   : "r"(a0), "r"(a1), "r"(a2), "r"(a3), "l"(db), "n"(TB));
  else asm volatile("{\n.reg .pred p;\nsetp.ne.b32 p, %38, 0;\nwgmma.mma_async.sync.aligned.m64n64k16.f32.bf16.bf16 {%0,%1,%2,%3,%4,%5,%6,%7,%8,%9,%10,%11,%12,%13,%14,%15,%16,%17,%18,%19,%20,%21,%22,%23,%24,%25,%26,%27,%28,%29,%30,%31}, {%32,%33,%34,%35}, %36, p, 1, 1, %37;\n}"
   : "+f"(d[O+0]), "+f"(d[O+1]), "+f"(d[O+2]), "+f"(d[O+3]), "+f"(d[O+4]), "+f"(d[O+5]), "+f"(d[O+6]), "+f"(d[O+7]), "+f"(d[O+8]), "+f"(d[O+9]), "+f"(d[O+10]), "+f"(d[O+11]), "+f"(d[O+12]), "+f"(d[O+13]), "+f"(d[O+14]), "+f"(d[O+15]), "+f"(d[O+16]), "+f"(d[O+17]), "+f"(d[O+18]), "+f"(d[O+19]), "+f"(d[O+20]), "+f"(d[O+21]), "+f"(d[O+22]), "+f"(d[O+23]), "+f"(d[O+24]), "+f"(d[O+25]), "+f"(d[O+26]), "+f"(d[O+27]), "+f"(d[O+28]), "+f"(d[O+29]), "+f"(d[O+30]), "+f"(d[O+31])
   : "r"(a0), "r"(a1), "r"(a2), "r"(a3), "l"(db), "n"(TB), "r"(sd));
}
template<int O,int TB,int ACC,int NN> __device__ __forceinline__ void mma_ss128(float (&d)[NN], uint64_t da, uint64_t db, int sd = 0){
  if constexpr (ACC == 1) asm volatile("wgmma.mma_async.sync.aligned.m64n128k16.f32.bf16.bf16 {%0,%1,%2,%3,%4,%5,%6,%7,%8,%9,%10,%11,%12,%13,%14,%15,%16,%17,%18,%19,%20,%21,%22,%23,%24,%25,%26,%27,%28,%29,%30,%31,%32,%33,%34,%35,%36,%37,%38,%39,%40,%41,%42,%43,%44,%45,%46,%47,%48,%49,%50,%51,%52,%53,%54,%55,%56,%57,%58,%59,%60,%61,%62,%63}, %64, %65, 1, 1, 1, %67, %66;"
   : "+f"(d[O+0]), "+f"(d[O+1]), "+f"(d[O+2]), "+f"(d[O+3]), "+f"(d[O+4]), "+f"(d[O+5]), "+f"(d[O+6]), "+f"(d[O+7]), "+f"(d[O+8]), "+f"(d[O+9]), "+f"(d[O+10]), "+f"(d[O+11]), "+f"(d[O+12]), "+f"(d[O+13]), "+f"(d[O+14]), "+f"(d[O+15]), "+f"(d[O+16]), "+f"(d[O+17]), "+f"(d[O+18]), "+f"(d[O+19]), "+f"(d[O+20]), "+f"(d[O+21]), "+f"(d[O+22]), "+f"(d[O+23]), "+f"(d[O+24]), "+f"(d[O+25]), "+f"(d[O+26]), "+f"(d[O+27]), "+f"(d[O+28]), "+f"(d[O+29]), "+f"(d[O+30]), "+f"(d[O+31]), "+f"(d[O+32]), "+f"(d[O+33]), "+f"(d[O+34]), "+f"(d[O+35]), "+f"(d[O+36]), "+f"(d[O+37]), "+f"(d[O+38]), "+f"(d[O+39]), "+f"(d[O+40]), "+f"(d[O+41]), "+f"(d[O+42]), "+f"(d[O+43]), "+f"(d[O+44]), "+f"(d[O+45]), "+f"(d[O+46]), "+f"(d[O+47]), "+f"(d[O+48]), "+f"(d[O+49]), "+f"(d[O+50]), "+f"(d[O+51]), "+f"(d[O+52]), "+f"(d[O+53]), "+f"(d[O+54]), "+f"(d[O+55]), "+f"(d[O+56]), "+f"(d[O+57]), "+f"(d[O+58]), "+f"(d[O+59]), "+f"(d[O+60]), "+f"(d[O+61]), "+f"(d[O+62]), "+f"(d[O+63])
   : "l"(da), "l"(db), "n"(TB & 1), "n"(TB >> 1));
  else if constexpr (ACC == 0) asm volatile("wgmma.mma_async.sync.aligned.m64n128k16.f32.bf16.bf16 {%0,%1,%2,%3,%4,%5,%6,%7,%8,%9,%10,%11,%12,%13,%14,%15,%16,%17,%18,%19,%20,%21,%22,%23,%24,%25,%26,%27,%28,%29,%30,%31,%32,%33,%34,%35,%36,%37,%38,%39,%40,%41,%42,%43,%44,%45,%46,%47,%48,%49,%50,%51,%52,%53,%54,%55,%56,%57,%58,%59,%60,%61,%62,%63}, %64, %65, 0, 1, 1, %67, %66;"
   : "=f"(d[O+0]), "=f"(d[O+1]), "=f"(d[O+2]), "=f"(d[O+3]), "=f"(d[O+4]), "=f"(d[O+5]), "=f"(d[O+6]), "=f"(d[O+7]), "=f"(d[O+8]), "=f"(d[O+9]), "=f"(d[O+10]), "=f"(d[O+11]), "=f"(d[O+12]), "=f"(d[O+13]), "=f"(d[O+14]), "=f"(d[O+15]), "=f"(d[O+16]), "=f"(d[O+17]), "=f"(d[O+18]), "=f"(d[O+19]), "=f"(d[O+20]), "=f"(d[O+21]), "=f"(d[O+22]), "=f"(d[O+23]), "=f"(d[O+24]), "=f"(d[O+25]), "=f"(d[O+26]), "=f"(d[O+27]), "=f"(d[O+28]), "=f"(d[O+29]), "=f"(d[O+30]), "=f"(d[O+31]), "=f"(d[O+32]), "=f"(d[O+33]), "=f"(d[O+34]), "=f"(d[O+35]), "=f"(d[O+36]), "=f"(d[O+37]), "=f"(d[O+38]), "=f"(d[O+39]), "=f"(d[O+40]), "=f"(d[O+41]), "=f"(d[O+42]), "=f"(d[O+43]), "=f"(d[O+44]), "=f"(d[O+45]), "=f"(d[O+46]), "=f"(d[O+47]), "=f"(d[O+48]), "=f"(d[O+49]), "=f"(d[O+50]), "=f"(d[O+51]), "=f"(d[O+52]), "=f"(d[O+53]), "=f"(d[O+54]), "=f"(d[O+55]), "=f"(d[O+56]), "=f"(d[O+57]), "=f"(d[O+58]), "=f"(d[O+59]), "=f"(d[O+60]), "=f"(d[O+61]), "=f"(d[O+62]), "=f"(d[O+63])
   : "l"(da), "l"(db), "n"(TB & 1), "n"(TB >> 1));
  else asm volatile("{\n.reg .pred p;\nsetp.ne.b32 p, %68, 0;\nwgmma.mma_async.sync.aligned.m64n128k16.f32.bf16.bf16 {%0,%1,%2,%3,%4,%5,%6,%7,%8,%9,%10,%11,%12,%13,%14,%15,%16,%17,%18,%19,%20,%21,%22,%23,%24,%25,%26,%27,%28,%29,%30,%31,%32,%33,%34,%35,%36,%37,%38,%39,%40,%41,%42,%43,%44,%45,%46,%47,%48,%49,%50,%51,%52,%53,%54,%55,%56,%57,%58,%59,%60,%61,%62,%63}, %64, %65, p, 1, 1, %67, %66;\n}"
   : "+f"(d[O+0]), "+f"(d[O+1]), "+f"(d[O+2]), "+f"(d[O+3]), "+f"(d[O+4]), "+f"(d[O+5]), "+f"(d[O+6]), "+f"(d[O+7]), "+f"(d[O+8]), "+f"(d[O+9]), "+f"(d[O+10]), "+f"(d[O+11]), "+f"(d[O+12]), "+f"(d[O+13]), "+f"(d[O+14]), "+f"(d[O+15]), "+f"(d[O+16]), "+f"(d[O+17]), "+f"(d[O+18]), "+f"(d[O+19]), "+f"(d[O+20]), "+f"(d[O+21]), "+f"(d[O+22]), "+f"(d[O+23]), "+f"(d[O+24]), "+f"(d[O+25]), "+f"(d[O+26]), "+f"(d[O+27]), "+f"(d[O+28]), "+f"(d[O+29]), "+f"(d[O+30]), "+f"(d[O+31]), "+f"(d[O+32]), "+f"(d[O+33]), "+f"(d[O+34]), "+f"(d[O+35]), "+f"(d[O+36]), "+f"(d[O+37]), "+f"(d[O+38]), "+f"(d[O+39]), "+f"(d[O+40]), "+f"(d[O+41]), "+f"(d[O+42]), "+f"(d[O+43]), "+f"(d[O+44]), "+f"(d[O+45]), "+f"(d[O+46]), "+f"(d[O+47]), "+f"(d[O+48]), "+f"(d[O+49]), "+f"(d[O+50]), "+f"(d[O+51]), "+f"(d[O+52]), "+f"(d[O+53]), "+f"(d[O+54]), "+f"(d[O+55]), "+f"(d[O+56]), "+f"(d[O+57]), "+f"(d[O+58]), "+f"(d[O+59]), "+f"(d[O+60]), "+f"(d[O+61]), "+f"(d[O+62]), "+f"(d[O+63])
   : "l"(da), "l"(db), "n"(TB & 1), "n"(TB >> 1), "r"(sd));
}
template<int O,int TB,int ACC,int NN> __device__ __forceinline__ void mma_rs128(float (&d)[NN], uint32_t a0, uint32_t a1, uint32_t a2, uint32_t a3, uint64_t db, int sd = 0){
  if constexpr (ACC == 1) asm volatile("wgmma.mma_async.sync.aligned.m64n128k16.f32.bf16.bf16 {%0,%1,%2,%3,%4,%5,%6,%7,%8,%9,%10,%11,%12,%13,%14,%15,%16,%17,%18,%19,%20,%21,%22,%23,%24,%25,%26,%27,%28,%29,%30,%31,%32,%33,%34,%35,%36,%37,%38,%39,%40,%41,%42,%43,%44,%45,%46,%47,%48,%49,%50,%51,%52,%53,%54,%55,%56,%57,%58,%59,%60,%61,%62,%63}, {%64,%65,%66,%67}, %68, 1, 1, 1, %69;"
   : "+f"(d[O+0]), "+f"(d[O+1]), "+f"(d[O+2]), "+f"(d[O+3]), "+f"(d[O+4]), "+f"(d[O+5]), "+f"(d[O+6]), "+f"(d[O+7]), "+f"(d[O+8]), "+f"(d[O+9]), "+f"(d[O+10]), "+f"(d[O+11]), "+f"(d[O+12]), "+f"(d[O+13]), "+f"(d[O+14]), "+f"(d[O+15]), "+f"(d[O+16]), "+f"(d[O+17]), "+f"(d[O+18]), "+f"(d[O+19]), "+f"(d[O+20]), "+f"(d[O+21]), "+f"(d[O+22]), "+f"(d[O+23]), "+f"(d[O+24]), "+f"(d[O+25]), "+f"(d[O+26]), "+f"(d[O+27]), "+f"(d[O+28]), "+f"(d[O+29]), "+f"(d[O+30]), "+f"(d[O+31]), "+f"(d[O+32]), "+f"(d[O+33]), "+f"(d[O+34]), "+f"(d[O+35]), "+f"(d[O+36]), "+f"(d[O+37]), "+f"(d[O+38]), "+f"(d[O+39]), "+f"(d[O+40]), "+f"(d[O+41]), "+f"(d[O+42]), "+f"(d[O+43]), "+f"(d[O+44]), "+f"(d[O+45]), "+f"(d[O+46]), "+f"(d[O+47]), "+f"(d[O+48]), "+f"(d[O+49]), "+f"(d[O+50]), "+f"(d[O+51]), "+f"(d[O+52]), "+f"(d[O+53]), "+f"(d[O+54]), "+f"(d[O+55]), "+f"(d[O+56]), "+f"(d[O+57]), "+f"(d[O+58]), "+f"(d[O+59]), "+f"(d[O+60]), "+f"(d[O+61]), "+f"(d[O+62]), "+f"(d[O+63])
   : "r"(a0), "r"(a1), "r"(a2), "r"(a3), "l"(db), "n"(TB));
  else if constexpr (ACC == 0) asm volatile("wgmma.mma_async.sync.aligned.m64n128k16.f32.bf16.bf16 {%0,%1,%2,%3,%4,%5,%6,%7,%8,%9,%10,%11,%12,%13,%14,%15,%16,%17,%18,%19,%20,%21,%22,%23,%24,%25,%26,%27,%28,%29,%30,%31,%32,%33,%34,%35,%36,%37,%38,%39,%40,%41,%42,%43,%44,%45,%46,%47,%48,%49,%50,%51,%52,%53,%54,%55,%56,%57,%58,%59,%60,%61,%62,%63}, {%64,%65,%66,%67}, %68, 0, 1, 1, %69;"
   : "=f"(d[O+0]), "=f"(d[O+1]), "=f"(d[O+2]), "=f"(d[O+3]), "=f"(d[O+4]), "=f"(d[O+5]), "=f"(d[O+6]), "=f"(d[O+7]), "=f"(d[O+8]), "=f"(d[O+9]), "=f"(d[O+10]), "=f"(d[O+11]), "=f"(d[O+12]), "=f"(d[O+13]), "=f"(d[O+14]), "=f"(d[O+15]), "=f"(d[O+16]), "=f"(d[O+17]), "=f"(d[O+18]), "=f"(d[O+19]), "=f"(d[O+20]), "=f"(d[O+21]), "=f"(d[O+22]), "=f"(d[O+23]), "=f"(d[O+24]), "=f"(d[O+25]), "=f"(d[O+26]), "=f"(d[O+27]), "=f"(d[O+28]), "=f"(d[O+29]), "=f"(d[O+30]), "=f"(d[O+31]), "=f"(d[O+32]), "=f"(d[O+33]), "=f"(d[O+34]), "=f"(d[O+35]), "=f"(d[O+36]), "=f"(d[O+37]), "=f"(d[O+38]), "=f"(d[O+39]), "=f"(d[O+40]), "=f"(d[O+41]), "=f"(d[O+42]), "=f"(d[O+43]), "=f"(d[O+44]), "=f"(d[O+45]), "=f"(d[O+46]), "=f"(d[O+47]), "=f"(d[O+48]), "=f"(d[O+49]), "=f"(d[O+50]), "=f"(d[O+51]), "=f"(d[O+52]), "=f"(d[O+53]), "=f"(d[O+54]), "=f"(d[O+55]), "=f"(d[O+56]), "=f"(d[O+57]), "=f"(d[O+58]), "=f"(d[O+59]), "=f"(d[O+60]), "=f"(d[O+61]), "=f"(d[O+62]), "=f"(d[O+63])
   : "r"(a0), "r"(a1), "r"(a2), "r"(a3), "l"(db), "n"(TB));
  else asm volatile("{\n.reg .pred p;\nsetp.ne.b32 p, %70, 0;\nwgmma.mma_async.sync.aligned.m64n128k16.f32.bf16.bf16 {%0,%1,%2,%3,%4,%5,%6,%7,%8,%9,%10,%11,%12,%13,%14,%15,%16,%17,%18,%19,%20,%21,%22,%23,%24,%25,%26,%27,%28,%29,%30,%31,%32,%33,%34,%35,%36,%37,%38,%39,%40,%41,%42,%43,%44,%45,%46,%47,%48,%49,%50,%51,%52,%53,%54,%55,%56,%57,%58,%59,%60,%61,%62,%63}, {%64,%65,%66,%67}, %68, p, 1, 1, %69;\n}"
   : "+f"(d[O+0]), "+f"(d[O+1]), "+f"(d[O+2]), "+f"(d[O+3]), "+f"(d[O+4]), "+f"(d[O+5]), "+f"(d[O+6]), "+f"(d[O+7]), "+f"(d[O+8]), "+f"(d[O+9]), "+f"(d[O+10]), "+f"(d[O+11]), "+f"(d[O+12]), "+f"(d[O+13]), "+f"(d[O+14]), "+f"(d[O+15]), "+f"(d[O+16]), "+f"(d[O+17]), "+f"(d[O+18]), "+f"(d[O+19]), "+f"(d[O+20]), "+f"(d[O+21]), "+f"(d[O+22]), "+f"(d[O+23]), "+f"(d[O+24]), "+f"(d[O+25]), "+f"(d[O+26]), "+f"(d[O+27]), "+f"(d[O+28]), "+f"(d[O+29]), "+f"(d[O+30]), "+f"(d[O+31]), "+f"(d[O+32]), "+f"(d[O+33]), "+f"(d[O+34]), "+f"(d[O+35]), "+f"(d[O+36]), "+f"(d[O+37]), "+f"(d[O+38]), "+f"(d[O+39]), "+f"(d[O+40]), "+f"(d[O+41]), "+f"(d[O+42]), "+f"(d[O+43]), "+f"(d[O+44]), "+f"(d[O+45]), "+f"(d[O+46]), "+f"(d[O+47]), "+f"(d[O+48]), "+f"(d[O+49]), "+f"(d[O+50]), "+f"(d[O+51]), "+f"(d[O+52]), "+f"(d[O+53]), "+f"(d[O+54]), "+f"(d[O+55]), "+f"(d[O+56]), "+f"(d[O+57]), "+f"(d[O+58]), "+f"(d[O+59]), "+f"(d[O+60]), "+f"(d[O+61]), "+f"(d[O+62]), "+f"(d[O+63])
   : "r"(a0), "r"(a1), "r"(a2), "r"(a3), "l"(db), "n"(TB), "r"(sd));
}

#define NEARLY 0
#define XAHEAD 3
#define HEADN 6
#define WBATCH 1
#define WB 8
#define WSLEEP 20
#define XSPREAD 4
#define NOSEND 0
#define MSPLIT 3
#define PFALL 1
#define L2PF 1
#define STAG 0
#define EPF 2
#define XNB 2
#define FNB 0
#define GNB 0
#define TH 5
#define PF0 4
#define FSPLIT 1
#define MGLU 1
#define SPC 2
#define TL 14
#define SPACE 40
#define WPF 1
#define WAFTER 7
#define WPACE 0
#define GATE_AT 4
#define TPACE 40
#define PFMODE 0
#define MAPMODE 1
template <int V> struct IC { static constexpr int value = V; };
struct Maps { CUtensorMap x, ft, g64, u64, e, wr, wi, xs, ts, t, g32, u32, d224, o; };

constexpr int NCTA = 130;
constexpr int U = 16384;
constexpr int TB = 36864;
constexpr int OFF_RING = 8 * U, OFF_Z = 12 * U, OFF_XB = 12 * U, OFF_T = 13 * U, OFF_D = OFF_T;
constexpr int OFF_BAR = 14 * U, OFF_SP = OFF_BAR + 512, OFF_G = OFF_SP + 1024 + 128;
constexpr int SMEM_BYTES = OFF_G + 512;
constexpr int B_FX = 0, B_FA = 8, B_FT = 12, B_Z = 16, B_W = 24, B_HX = 25, B_TL = 26, B_HP = 27, B_WR = 30, B_E0 = 34;
constexpr int B_EA = 35, B_ET = 39, B_PZ = 43, B_RDY = 45, B_FE = 46;
constexpr int B_T = 50, B_XS = 51, B_G = 53, B_RD0 = 54, NBAR = 55;
__host__ __device__ constexpr int rslot(int n) { return n & 3; }
__host__ __device__ constexpr int rpar(int n) { return (n >> 2) & 1; }

__global__ void __cluster_dims__(2, 1, 1) __launch_bounds__(512, 1)
fused_kernel(Work* __restrict__ ws, const uint16_t* __restrict__ dtab, const __nv_bfloat16* __restrict__ w_r, const __nv_bfloat16* __restrict__ w_i,
             const __nv_bfloat16* __restrict__ gate_w, const __nv_bfloat16* __restrict__ x, const __grid_constant__ Maps maps) {
  extern __shared__ __align__(1024) uint8_t smem[];
  if (threadIdx.x < 32 && elect_one()) {
#pragma unroll
    for (int i = 0; i < PF0; i++) asm volatile("prefetch.tensormap [%0];" ::"l"((const char*)&maps + i * 128) : "memory");
  }
  const uint32_t sb = smem_u32(smem);
  const uint32_t bars = sb + OFF_BAR;
  const int tid = threadIdx.x, lane = tid & 31;
  const int warp = __shfl_sync(0xffffffffu, tid >> 5, 0);
  const bool helper = blockIdx.x >= 128;
  const int cl = (blockIdx.x >> 1) & 63, rank = blockIdx.x & 1;
  const int q4 = (cl & 1) | ((cl >> 2) & 2), rb = ((cl >> 1) & 3) | ((cl >> 4) << 2);
  const int j = 2 * q4 + rank;
  const int f_full = 448 * q4 + (rank ? 256 : 0);
  const int f_half = 448 * q4 + (rank ? 224 : 192);
  const int kg = 2 * j + (rb >> 3), tn = rb & 7;

  if (tid == 64) { PROF_EV(0); PROF_CK(40); }
  if (warp < 8) {
    if (!helper && tid < 32) {
      const int r = 16 * j + (tid & 15);
      asm volatile("prefetch.global.L2 [%0];" ::"l"(x + (size_t)(2 * rb + (r >> 6) + 32 * (r & 63)) * 512 + 64 * (tid >> 4)));
    }
    asm volatile("barrier.cluster.arrive.relaxed.aligned;" ::: "memory");
    asm volatile("setmaxnreg.inc.sync.aligned.u32 192;");
    if (!helper) {
      const int wg = warp >> 2, w = warp & 3, g = lane >> 2;
      const bool elect = (tid & 127) == 0;
      float cX[32], cA[64], cB[64], cC[64], ci[64], ct[64];
      const int zero = blockIdx.x >> 16;
      uint32_t h[56], yf[16];
      const uint32_t d0 = (sb & 0x3FFFF) >> 4;
      const uint32_t dK = d0 | (1u << 16), dN = d0 | (512u << 16);
      const uint32_t dX = dK + wg * 512;
      constexpr uint32_t RING = OFF_RING >> 4;
      auto waitA = [&](int n) { mbar_wait(bars + 8 * (B_FA + rslot(n)), rpar(n)); };
      auto freeA = [&](int n) { mbar_arrive_if(elect, bars + 8 * (B_EA + rslot(n))); };
      auto nop = [] {};

      asm volatile("bar.sync 0, 384;" ::: "memory");
#pragma unroll 1
      for (int i = 0; i < 4; i++) {
        const uint64_t dx = d128(dX + i * 2048), df = d128(dK + (OFF_XB >> 4) + (i & 1) * 1024);
        mbar_wait(bars + 8 * (B_FX + 2 * i), 0);
        wg_fence();
        mma_ss64<0, 0, 2>(cX, df, dx, i);
        mma_ss64<0, 0, 1>(cX, df + 2, dx + 2);
        wg_commit(); wg_wait<1>();
        mbar_arrive_if(elect && i, bars + 8 * (B_EA + rslot(i - 1)));
        mma_ss64<0, 0, 1>(cX, df + 4, dx + 4);
        mma_ss64<0, 0, 1>(cX, df + 6, dx + 6);
        if (i == 0 && tid == 0) PROF_EV(1);
        mbar_wait(bars + 8 * (B_FX + 2 * i + 1), 0);
        wg_fence();
#pragma unroll
        for (int k = 0; k < 4; k++) mma_ss64<0, 0, 1>(cX, df + (512 + k * 2), dx + (1024 + k * 2));
        wg_commit();
        waitA(i);
        wg_fence();
        const uint64_t da = d128(dX + i * 1024), db = d128(dN + RING + i * 1024);
        mma_ss128<0, 1, 2>(cA, da, db, i);
        wg_commit(); wg_wait<1>();
        mbar_arrive_if(elect, bars + 8 * (B_FE + i));
#pragma unroll
        for (int k = 1; k < 4; k++) mma_ss128<0, 1, 1>(cA, da + k * 2, db + k * 128);
        wg_commit();
      }
      fence_regs<0, 32>(cX);
#pragma unroll
      for (int e = 0; e < 16; e++) yf[e] = pack_pin(cX[2 * e], cX[2 * e + 1]);
      if (tid == 0) { PROF_EV(2); PROF_CK(42); }
      {
        waitA(4); mbar_wait(bars + 8 * B_E0, 0);
        const uint64_t de = d128(dN + (wg ? RING : OFF_XB >> 4));
        wg_fence();
        mma_rs128<0, 1, 0>(cB, yf[0], yf[1], yf[2], yf[3], de);
        wg_commit();
        wg_wait<1>();
        freeA(3);
#pragma unroll
        for (int k = 1; k < 4; k++) mma_rs128<0, 1, 1>(cB, yf[4 * k], yf[4 * k + 1], yf[4 * k + 2], yf[4 * k + 3], de + k * 128);
        wg_commit();
      }
      bool rel = false;
      auto acquire = [&](int n) {
        rel = elect;
        if (!mbar_try(bars + 8 * (B_FA + rslot(n)), rpar(n))) { wg_wait<0>(); freeA(n - 1); rel = false; waitA(n); }
      };
      auto freeP = [&](int n) { mbar_arrive_if(rel, bars + 8 * (B_EA + rslot(n - 1))); };
      auto ffn_step = [&](auto first, auto split, float (&acc)[64], int n, int kb, auto done, auto work) {
        constexpr int SPLIT = decltype(split)::value;
        acquire(n);
        wg_fence();
        const uint64_t dx = d128(dX + kb * 1024), db = d128(dN + RING + rslot(n) * 1024);
        mma_ss128<0, 1, decltype(first)::value>(acc, dx, db, kb);
#pragma unroll
        for (int k = 1; k < SPLIT; k++) mma_ss128<0, 1, 1>(acc, dx + k * 2, db + k * 128);
        wg_commit();
        work();
        wg_wait<1>();
        freeP(n);
        done();
        if (SPLIT < 4) {
          wg_fence();
#pragma unroll
          for (int k = SPLIT; k < 4; k++) mma_ss128<0, 1, 1>(acc, dx + k * 2, db + k * 128);
          wg_commit();
        }
      };
      {
        const int s0 = 2 * rb + wg, kr = 2 * ((s0 & 1) | ((s0 & 4) >> 1));
        const int m = lane >> 3, r = lane & 7;
        const uint32_t a0 = sb + OFF_XB + wg * 8192 + (((w >> 1) * 8 + (m >> 1)) * 2 + (w & 1)) * 256 + (m & 1) * 128 + ((r ^ (kr + (m & 1))) << 4);
        ffn_step(IC<1>(), IC<4>(), cA, 5, 4, [&] { fence_regs<0, 64>(cB); }, nop);
        asm volatile("bar.sync 5, 256;" ::: "memory");
        auto stage = [&](int i) {
          stsm4t(a0 + i * 1024, pack_bf16(cB[8 * i] - cB[34 + 8 * i], cB[8 * i + 1] - cB[35 + 8 * i]),
                 pack_bf16(cB[32 + 8 * i] + cB[8 * i + 2], cB[33 + 8 * i] + cB[8 * i + 3]),
                 pack_bf16(cB[8 * i + 4] - cB[38 + 8 * i], cB[8 * i + 5] - cB[39 + 8 * i]),
                 pack_bf16(cB[36 + 8 * i] + cB[8 * i + 6], cB[37 + 8 * i] + cB[8 * i + 7]));
          if (j == 0 && w == 0) {
            const uint32_t a1 = r ? sb + OFF_SP + 1024 : sb + OFF_SP + wg * 512 + (m & 1) * 256 + (m >> 1) * 128;
#pragma unroll
            for (int n = 2 * i; n < 2 * i + 2; n++)
              asm volatile("stmatrix.sync.aligned.m8n8.x4.shared.b16 [%0], {%1,%2,%3,%4};" ::"r"(a1 + ((n ^ (kr + (m >> 1)) ^ r) << 4)),
                           "r"(pack_bf16(cB[4 * n], cB[4 * n + 1])), "r"(pack_bf16(cB[4 * n + 2], cB[4 * n + 3])),
                           "r"(pack_bf16(cB[32 + 4 * n], cB[33 + 4 * n])), "r"(pack_bf16(cB[34 + 4 * n], cB[35 + 4 * n])) : "memory");
          }
        };
        auto publish = [&] {
          asm volatile("fence.proxy.async.shared::cta;" ::: "memory");
          __syncwarp();
          mbar_arrive_if(lane == 0, bars + 8 * (B_XS + wg));
          if (tid == 0) PROF_EV(3);
        };
        stage(0);
        ffn_step(IC<1>(), IC<FSPLIT>(), cA, 6, 5, nop, nop);
        stage(1);
        ffn_step(IC<1>(), IC<FSPLIT>(), cA, 7, 6, nop, nop);
        stage(2);
        ffn_step(IC<1>(), IC<2>(), cA, 8, 7, [&] { stage(3); }, nop);
        publish();
      }
      float g0 = 0.f, g1 = 0.f;
      uint32_t tag = 0;
      uint32_t ob[2] = {0, 0};
      auto glu = [&](auto& acc, int half, int ho, int i0, int i1) {
#pragma unroll
        for (int i = i0; i < i1; i++)
          asm volatile("{\n.reg .b32 a, b;\ncvt.rn.relu.bf16x2.f32 a, %2, %1;\ncvt.rn.bf16x2.f32 b, %4, %3;\nmul.rn.bf16x2 a, a, b;\nmul.rn.bf16x2 %0, a, %5;\n}"
                       : "=r"(h[ho + i]) : "f"(acc[2 * i]), "f"(acc[2 * i + 1]), "f"(acc[half + 2 * i]), "f"(acc[half + 1 + 2 * i]), "r"(ob[i & 1]) : "memory");
      };
      ffn_step(IC<2>(), IC<1>(), cB, 9, zero, nop, nop);
#pragma unroll 1
      for (int kb = 1; kb < 8; kb++)
        ffn_step(IC<1>(), IC<FSPLIT>(), cB, 9 + kb, kb, nop, [&] {
          if (kb == 4 + 2 * wg) {
            mbar_wait(bars + 8 * B_G, 0);
            const uint32_t gb0 = *(const uint32_t*)(smem + OFF_G + (wg * 64 + w * 16 + g) * 4), gb1 = *(const uint32_t*)(smem + OFF_G + (wg * 64 + w * 16 + g + 8) * 4);
            tag = gb0 & 1; g0 = __uint_as_float(gb0 & ~1u); g1 = __uint_as_float(gb1 & ~1u);
            ob[0] = pack_bf16(1.0f - g0, 1.0f - g0); ob[1] = pack_bf16(1.0f - g1, 1.0f - g1);
            glu(cA, 32, 0, 0, 16);
          }
        });
      if (tid == 0) { PROF_EV(4); PROF_CK(43); }
      auto m_step = [&](auto first, int i) {
        acquire(17 + i);
        wg_fence();
        const uint64_t dx = d128(dX + i * 2048), dm = d64(dN + RING + rslot(17 + i) * 1024);
        mma_ss64<0, 1, decltype(first)::value>(ct, dx, dm);
#pragma unroll
        for (int k = 1; k < MSPLIT; k++) mma_ss64<0, 1, 1>(ct, dx + ((k >> 2) * 1024 + (k & 3) * 2), dm + k * 64);
        wg_commit();
        wg_wait<1>();
        freeP(17 + i);
        wg_fence();
#pragma unroll
        for (int k = MSPLIT; k < 8; k++) mma_ss64<0, 1, 1>(ct, dx + ((k >> 2) * 1024 + (k & 3) * 2), dm + k * 64);
        wg_commit();
      };
      m_step(IC<0>(), 0);
#pragma unroll 1
      for (int i = 1; i < 5; i++) {
        if (i == 1 + 2 * wg) glu(cB, 32, 16, 0, 16);
        if (i < 4) m_step(IC<1>(), i);
      }
      if (tid == 0) { PROF_EV(5); PROF_CK(44); }
      ffn_step(IC<0>(), IC<1>(), cC, 21, 0, nop, nop);
#pragma unroll 1
      for (int kb = 1; kb < 8; kb++)
        ffn_step(IC<1>(), IC<FSPLIT>(), cC, 21 + kb, kb, [&] { mbar_arrive_if(elect && !(kb & 1), bars + 8 * (B_ET + (kb >> 1) - 1)); }, [&] {
          if (kb == 1 + wg) glu(ct, 16, 48, 0, 8);
        });

      auto twait = [&](uint32_t bar, uint32_t par, int) { mbar_wait(bar, par); };
      const int fo = warp * 128 + lane;
      auto fetch = [&](uint4 (&pv)[4], int z) {
        twait(bars + 8 * (z < 4 ? B_Z + 2 * z + wg : B_HP + z - 4), 0, 8 + z);
        const uint8_t* src = smem + (z < 4 ? OFF_Z - z * U : z == 4 ? OFF_T : (z - 5) * U) + fo * 16;
#pragma unroll
        for (int i = 0; i < 4; i++) pv[i] = *(const uint4*)(src + i * 512);
      };
      auto check = [&](uint4 (&pv)[4], int z) {
        const uint32_t t0 = (uint32_t)clock();
        while (__any_sync(0xffffffffu, ((pv[0].x ^ tag) | (pv[1].x ^ tag) | (pv[2].x ^ tag) | (pv[3].x ^ tag)) & 1)) {
#pragma unroll
          for (int i = 0; i < 4; i++) pv[i] = ld_x4(ws->part + (size_t)((rb * 8 + j) * 3 + z - 4) * 1024 + fo + i * 32);
          spin_guard(t0);
        }
#pragma unroll
        for (int i = 0; i < 4; i++) pv[i].x &= ~1u;
      };
      const uint32_t peerZ = mapa(sb + OFF_Z + fo * 16, rank ^ 1), peerB = mapa(bars + 8 * (B_Z + wg), rank ^ 1);
      auto tile_mma = [&](auto off, int t, int k0, int k1, int init) {
        constexpr int O = decltype(off)::value;
        const uint64_t db = d128(dN + (t & 3) * (TB >> 4)), dw = db + rank * 256, dm = db + (rank ? 0 : 1536);
#pragma unroll
        for (int k = k0; k < k1; k++) {
          if (k == 0) mma_rs64<O, 1, 2>(ct, h[0], h[1], h[2], h[3], dw, init);
          else if (k < 14) mma_rs64<O, 1, 1>(ct, h[4 * k], h[4 * k + 1], h[4 * k + 2], h[4 * k + 3], k < 12 ? dw + k * 128 : dm + (k - 12) * 128);
          else mma_rs64<O, 1, 1>(ct, yf[4 * k - 56], yf[4 * k - 55], yf[4 * k - 54], yf[4 * k - 53], db + k * 128);
        }
      };
      uint4 pv[4];
      auto tile = [&](auto off, int t) {
        constexpr int P = 32 - decltype(off)::value;
        const bool grid = t >= 4 && t < 7, pre = t >= 3 && t != 6;
        const int zo = grid ? t - 4 : t == 7 ? 3 : t - 1, z = t - 3;
        const int owner = rb * 8 + 2 * ((q4 + zo + 1) & 3) + rank;
        uint4* dst = ws->part + (size_t)(owner * 3 + zo) * 1024 + fo;
        const uint32_t src = sb + (z < 4 ? OFF_Z - z * U : OFF_T) + fo * 16;
        twait(bars + 8 * (B_FT + (t & 3)), t >> 2, t);
        wg_fence();
        tile_mma(off, t, 0, TH, zero);
        wg_commit();
        wg_wait<1>();
        mbar_arrive_if(elect && t < 6, bars + 8 * (B_ET + t - 1));
        if (t < 3) twait(bars + 8 * (t == 1 ? B_RD0 : B_RDY), 0, 14 + t);
        fence_regs<P, 32>(ct);
        uint32_t pk[16];
#pragma unroll
        for (int i = 0; i < 16; i++) pk[i] = pack_bf16(ct[P + 2 * i], ct[P + 2 * i + 1]);
        if (grid) {
#pragma unroll
          for (int i = 0; i < 4; i++) {
            pk[4 * i] = (add_bf2(pk[4 * i], pv[i].x) & ~1u) | tag; pk[4 * i + 1] = add_bf2(pk[4 * i + 1], pv[i].y);
            pk[4 * i + 2] = add_bf2(pk[4 * i + 2], pv[i].z); pk[4 * i + 3] = add_bf2(pk[4 * i + 3], pv[i].w);
          }
        }
        wg_fence();
#pragma unroll
        for (int i = 0; i < 4; i++) {
          asm volatile(
              "{\n.reg .pred p;\nsetp.ne.b32 p, %7, 0;\n@p st.relaxed.gpu.global.v4.u32 [%0], {%3,%4,%5,%6};\n"
              "@!p st.async.weak.shared::cluster.mbarrier::complete_tx::bytes.v4.b32 [%1], {%3,%4,%5,%6}, [%2];\n}" ::"l"(dst + i * 32),
              "r"(peerZ - zo * U + i * 512), "r"(peerB + 16 * zo), "r"(pk[4 * i]), "r"(pk[4 * i + 1]), "r"(pk[4 * i + 2]),
              "r"(pk[4 * i + 3]), "r"((int)grid) : "memory");
          if (i == 3) hint_add_if(grid && lane == 0, &ws->cntP[32 * owner + zo]);
          tile_mma(off, t, TH + SPC * i, i < 3 ? TH + SPC * i + SPC : TL, 0);
        }
        wg_commit();
        if (pre) twait(bars + 8 * (z < 4 ? B_Z + 2 * z + wg : B_HP), 0, 8 + z);
        wg_fence();
#pragma unroll
        for (int i = 0; i < 4; i++) {
          asm volatile("{\n.reg .pred p;\nsetp.ne.b32 p, %5, 0;\n@p ld.shared.v4.u32 {%0,%1,%2,%3}, [%4];\n}"
                       : "=r"(pv[i].x), "=r"(pv[i].y), "=r"(pv[i].z), "=r"(pv[i].w) : "r"(src + i * 512), "r"((int)pre) : "memory");
          tile_mma(off, t, TL + i, i < 3 ? TL + 1 + i : 18, 0);
        }
        wg_commit();
      };
      asm volatile("barrier.cluster.wait.aligned;" ::: "memory");
      twait(bars + 8 * B_FT, 0, 0);
      wg_fence();
      tile_mma(IC<0>(), 0, 0, 5, zero);
      wg_commit();
      wg_wait<1>();
      mbar_arrive_if(elect, bars + 8 * (B_ET + 3));
      glu(cC, 32, 32, 0, 8);
      waitA(29 + wg);
      wg_fence();
      tile_mma(IC<0>(), 0, 5, 8, 0);
      tile_mma(IC<0>(), 0, 12, 14, 0);
      wg_commit();
      glu(cC, 32, 32, 8, 16);
      if (tid == 0) PROF_EV(6);
      if (tid == 128) PROF_EV(27);
      mbar_wait(bars + 8 * (j == 0 ? B_T : B_TL), 0);
      if (tid == 0) { PROF_EV(7); PROF_CK(45); }
      wg_fence();
      {
        const uint64_t dt = d128(dN + (OFF_T >> 4) + wg * 512), de = d128(dK + RING + (1 + wg) * 1024);
        mma_ss64<0, 1, 0>(ci, de, dt);
        mma_ss64<32, 1, 0>(ci, de + 512, dt);
#pragma unroll
        for (int k = 1; k < 4; k++) {
          mma_ss64<0, 1, 1>(ci, de + k * 2, dt + k * 128);
          mma_ss64<32, 1, 1>(ci, de + (512 + k * 2), dt + k * 128);
        }
        wg_commit();
      }
      tile_mma(IC<0>(), 0, 8, 12, 0);
      wg_commit();
      wg_wait<1>();
      if (elect) asm volatile("mbarrier.arrive.shared::cluster.b64 _, [%0];" ::"r"(mapa(bars + 8 * B_RDY, rank ^ 1)) : "memory");
      mbar_arrive_if(elect, bars + 8 * (B_PZ + 1));
      fence_regs<0, 64>(ci);
#pragma unroll
      for (int i = 0; i < 16; i++) {
        const float gg = ((i & 1) ? g1 : g0) * (2.0f / (2048.0f * 512.0f));
        if (i & 2) yf[i] = pack_pin((ci[2 * i] - ci[28 + 2 * i]) * gg, (ci[2 * i + 1] - ci[29 + 2 * i]) * gg);
        else yf[i] = pack_pin((ci[2 * i] + ci[36 + 2 * i]) * gg, (ci[2 * i + 1] + ci[37 + 2 * i]) * gg);
      }
      wg_fence();
      tile_mma(IC<0>(), 0, 14, 18, 0);
      wg_commit();
      if (tid == 0) PROF_EV(8);
      if (tid == 128) PROF_EV(28);
#pragma unroll 1
      for (int t = 1;; t += 2) {
        tile(IC<32>(), t);
        if (t == 7) break;
        tile(IC<0>(), t + 1);
      }
      if (tid == 0) { PROF_EV(9); PROF_CK(46); }
      if (tid == 128) PROF_EV(29);
      {
        uint4 p1[4], p2[4], p3[4];
        fetch(p1, 5);
        fetch(p3, 3);
        if (tid == 0) PROF_EV(25);
        fetch(p2, 6);
        if (tid == 0) PROF_EV(24);
        check(pv, 4); check(p1, 5); check(p2, 6);
        uint32_t ps[16];
#pragma unroll
        for (int i = 0; i < 4; i++) {
          ps[4 * i] = add_bf2(add_bf2(pv[i].x, p1[i].x), add_bf2(p2[i].x, p3[i].x)); ps[4 * i + 1] = add_bf2(add_bf2(pv[i].y, p1[i].y), add_bf2(p2[i].y, p3[i].y));
          ps[4 * i + 2] = add_bf2(add_bf2(pv[i].z, p1[i].z), add_bf2(p2[i].z, p3[i].z)); ps[4 * i + 3] = add_bf2(add_bf2(pv[i].w, p1[i].w), add_bf2(p2[i].w, p3[i].w));
        }
        if (tid == 0) PROF_EV(14);
        wg_wait<0>();
        fence_regs<32, 32>(ct);
        float sum[32];
#pragma unroll
        for (int i = 0; i < 16; i++) { sum[2 * i] = ct[32 + 2 * i] + bf_lo(ps[i]); sum[2 * i + 1] = ct[33 + 2 * i] + bf_hi(ps[i]); }
        const uint32_t stg = sb + OFF_T + warp * 2048;
        const int mr = (lane & 7) + ((lane >> 3) & 1) * 8, mc = lane >> 4;
#pragma unroll
        for (int i = 0; i < 4; i++) {
          const uint32_t a = stg + mr * 128 + (((2 * i + mc) ^ (mr & 7)) << 4);
          asm volatile("stmatrix.sync.aligned.m8n8.x4.shared.b16 [%0], {%1,%2,%3,%4};" ::"r"(a), "r"(pack_bf16(sum[8 * i], sum[8 * i + 1])),
                       "r"(pack_bf16(sum[8 * i + 2], sum[8 * i + 3])), "r"(pack_bf16(sum[8 * i + 4], sum[8 * i + 5])),
                       "r"(pack_bf16(sum[8 * i + 6], sum[8 * i + 7])) : "memory");
        }
        asm volatile("fence.proxy.async.shared::cta;" ::: "memory");
        __syncwarp();
        if (elect_one()) {
          asm volatile("cp.async.bulk.tensor.3d.global.shared::cta.bulk_group [%0, {%2, %3, %4}], [%1];" ::"l"(&maps.o), "r"(stg), "r"(64 * j),
                       "r"(16 * w), "r"(2 * rb + wg) : "memory");
          asm volatile("cp.async.bulk.commit_group;\ncp.async.bulk.wait_group.read 0;" ::: "memory");
        }
      }
      if (tid == 0) { PROF_EV(15); PROF_CK(41); }
      if (tid == 128) PROF_EV(30);
    }
  } else if (warp < 12) {
    asm volatile("setmaxnreg.dec.sync.aligned.u32 104;");
    asm volatile("barrier.cluster.arrive.relaxed.aligned;" ::: "memory");
    const int t = tid - 256, w = warp - 8;
    const uint32_t ep = ld_x1(&ws->epoch[blockIdx.x * 8]);
    const uint32_t tag = (ep + 1) & 1;
    auto w_issue = [&](const CUtensorMap* m) {

      if (elect_one()) { mbar_expect_tx(bars + 8 * (B_WR + w), 3072); tma4d(sb + OFF_T + w * 3072, m, bars + 8 * (B_WR + w), 16 * kg, 0, 2 * w, tn); }

          __syncwarp();
    };
    auto gate_rows = [&] {
      const int r = 16 * j + 4 * w + (lane >> 3);
      const uint4* pg = (const uint4*)gate_w + (lane & 7);
      {
        float a = 0.f;
        asm volatile("bar.sync 4, 256;" ::: "memory");
#pragma unroll 1
        for (int hf = 0; hf < 2; hf++) {
          uint4 v[4], u[4];
#pragma unroll
          for (int kb = 0; kb < 4; kb++) v[kb] = __ldg(pg + (4 * hf + kb) * 8);
          mbar_wait(bars + 8 * (B_FE + 1 + 2 * hf), 0);
          if (hf) w_issue(&maps.wr);
#pragma unroll
          for (int kb = 0; kb < 4; kb++) u[kb] = *(const uint4*)(smem + (4 * hf + kb) * U + r * 128 + (((lane ^ r) & 7) << 4));
#pragma unroll
          for (int kb = 0; kb < 4; kb++) {
            const uint32_t uu[4] = {u[kb].x, u[kb].y, u[kb].z, u[kb].w}, vv[4] = {v[kb].x, v[kb].y, v[kb].z, v[kb].w};
#pragma unroll
            for (int e = 0; e < 4; e++) {
              uint32_t pr;
              asm("mul.rn.bf16x2 %0, %1, %2;" : "=r"(pr) : "r"(uu[e]), "r"(vv[e]));
              a += bf_lo(pr) + bf_hi(pr);
            }
          }
        }
#pragma unroll
        for (int o = 4; o; o >>= 1) a += __shfl_xor_sync(0xffffffffu, a, o);
        if ((lane & 7) == 0)
          asm volatile("st.relaxed.gpu.global.u32 [%0], %1;" ::"l"(ws->gate + rb * 128 + r),
                       "r"(pack_bf16(0.f, __fdividef(1.0f, 1.0f + __expf(-bf_lo(pack_bf16(a, 0.f))))) | tag) : "memory");
        if (t == 0) PROF_EV(18);
      }
    };
    {
      const int g = lane >> 2, q = lane & 3;
      uint32_t wf[32];
      if (!helper) {
        gate_rows();
        const uint32_t wa = sb + OFF_T + w * (3072 + 4) + q * 48 + g * 2;
#pragma unroll 1
        for (int ri = 0; ri < 2; ri++) {
          mbar_wait(bars + 8 * (B_WR + w), ri);
#pragma unroll
          for (int n2 = 0; n2 < 32 / WB; n2++) {
            uint32_t v[WB];
#pragma unroll
            for (int i = 0; i < WB; i++) {
              const int e = n2 * WB + i;
              asm volatile("ld.shared.u16 %0, [%1];" : "=r"(v[i]) : "r"(wa + ((e >> 1) & 7) * 192 + (e & 1) * (1536 + 2) + (e >> 4) * 16) : "memory");
            }
#pragma unroll
            for (int i = 0; i < WB; i++) wf[n2 * WB + i] = __byte_perm(wf[n2 * WB + i], v[i], 0x5432);
            if (WSLEEP) { asm volatile("nanosleep.u32 %0;" ::"r"(WSLEEP + (v[WB - 1] >> 16)) : "memory"); }
          }
          __syncwarp();
          if (ri == 0) w_issue(&maps.wi);
        }
        asm volatile("bar.sync 1, 128;" ::: "memory");
        if (t == 0) PROF_EV(11);
      } else {
        asm volatile("bar.sync 4, 256;" ::: "memory");
        hint_wait(&ws->cntW[0], (ep + 1) * 128u);
        const uint32_t t0 = (uint32_t)clock();
#pragma unroll 1
        for (;;) {
          uint32_t bad = 0;
#pragma unroll
          for (int i = 0; i < 32; i++) {
            const float2 v = ld_x2((const float2*)ws->Wh + (i >> 4) * 2048 + 16 * w + g + 8 * (i & 1) + 64 * q + ((i >> 1) & 7) * 256);
            wf[i] = __float_as_uint(v.x); bad |= __float_as_uint(v.y) ^ tag;
          }
          if (!__any_sync(0xffffffffu, bad & 1)) break;
          spin_guard(t0);
        }
        if (t == 0) PROF_EV(11);
      }
      if (w == 0 && elect_one()) { mbar_expect_tx(bars + 8 * B_W, 8192); bulk_load(sb + OFF_D, dtab, 8192, bars + 8 * B_W); }
      asm volatile("barrier.cluster.wait.aligned;" ::: "memory");
      mbar_wait(bars + 8 * B_W, 0);
      mbar_wait(bars + 8 * B_HX, 0);
      if (t == 0) PROF_EV(12);
      const uint32_t dd = (sb & 0x3FFFF) >> 4;
      const uint64_t dF = d128((dd + (OFF_D >> 4)) | (512u << 16)), dI = d128((dd + (OFF_D >> 4)) | (1u << 16)), dA = d128((dd + (OFF_XB >> 4)) | (512u << 16));
      float az[32];
      const int zero = blockIdx.x >> 16;
      uint32_t pf[32];
#pragma unroll
      for (int mt = 0; mt < 2; mt++) {
        wg_fence();
        if (mt == 0) mma_ss64<0, 3, 0>(az, dA, dF);
        else mma_ss64<0, 3, 2>(az, dA + 512, dF, zero);
#pragma unroll
        for (int k = 1; k < 4; k++) mma_ss64<0, 3, 1>(az, dA + (mt * 512 + k * 128), dF + k * 128);
        wg_commit();
        wg_wait<0>();
        fence_regs<0, 32>(az);
#pragma unroll
        for (int i = 0; i < 16; i++) {
          const float wr = bf_lo(wf[16 * mt + i]), wi = bf_hi(wf[16 * mt + i]);
          pf[16 * mt + i] = pack_pin(fmaf(az[2 * i], wr, -az[2 * i + 1] * wi), fmaf(az[2 * i], wi, az[2 * i + 1] * wr));
        }
      }
      if (t == 0) PROF_EV(16);
      {
        const int m = lane >> 3, r = lane & 7;
        const int sl = 2 * (m >> 1) + ((r >> 1) & 1) + 4 * (r >> 2);
        const uint32_t a0 = sb + OFF_XB + (2 * w + (m & 1)) * 2048 + sl * 64;
        uint32_t pk[16];
#pragma unroll
        for (int mt = 0; mt < 3; mt++) {
          if (mt < 2) {
            wg_fence();
            mma_rs64<0, 0, 2>(az, pf[16 * mt], pf[16 * mt + 1], pf[16 * mt + 2], pf[16 * mt + 3], dI, mt ? (int)helper : zero);
#pragma unroll
            for (int k = 1; k < 4; k++) mma_rs64<0, 0, 1>(az, pf[16 * mt + 4 * k], pf[16 * mt + 4 * k + 1], pf[16 * mt + 4 * k + 2], pf[16 * mt + 4 * k + 3], dI + k * 2);
            wg_commit();
          }
          if (mt > 0 && !helper) {
#pragma unroll
            for (int i = 0; i < 4; i++) stsm4t(a0 + ((((mt - 1) * 2 + (r & 1)) ^ (sl >> 1)) << 4) + i * 512, pk[4 * i], pk[4 * i + 1], pk[4 * i + 2], pk[4 * i + 3]);
          }
          if (mt < 2) {
            wg_wait<0>();
            fence_regs<0, 32>(az);
#pragma unroll
            for (int i = 0; i < 16; i++) pk[i] = pack_pin(az[2 * i], az[2 * i + 1]);
          }
        }
      }
      if (helper) {
#pragma unroll
        for (int i = 0; i < 16; i++) {
          const int n = i >> 1, s0 = 8 * (n >> 1) + 2 * (n & 1) + (q & 1) + 4 * (q >> 1);
          if ((n & 1) == (int)(blockIdx.x & 1)) st_u2(ws->Ts + s0 * 64 + 16 * w + g + 8 * (i & 1), pack_bf16(az[2 * i], az[2 * i + 1]), tag);
        }
        __syncwarp();
        hint_add_if(lane == 0, &ws->cntH[0]);
        if (t == 0) { ws->epoch[blockIdx.x * 8] = ep + 1; PROF_EV(13); }
      } else {
        asm volatile("fence.proxy.async.shared::cta;" ::: "memory");
        __syncwarp();
        if (elect_one()) {
          if (t == 0) PROF_EV(17);
          if (SPACE) __nanosleep(SPACE * w);
          asm volatile("cp.async.bulk.tensor.3d.global.shared::cta.bulk_group [%0, {%2, %3, %4}], [%1];" ::"l"(&maps.ts), "r"(sb + OFF_XB + w * 4096),
                       "r"(32 * kg), "r"(0), "r"(8 * tn + 2 * w) : "memory");
          bulk_done_signal(&ws->cntT[32 * j]);
          asm volatile("mbarrier.arrive.shared::cluster.b64 _, [%0];" ::"r"(mapa(bars + 8 * B_RD0, rank ^ 1)) : "memory");
          if (t == 96) PROF_EV(13);
        }
        __syncwarp();
        if (j == 0) {
          hint_wait(&ws->cntH[0], (ep + 1) * 8u);
          const uint32_t t0 = (uint32_t)clock();
          float2 v;
          do { v = ld_x2((const float2*)ws->Ts + 2 * rb * 64 + t); spin_guard(t0); } while (__any_sync(0xffffffffu, (__float_as_uint(v.y) ^ tag) & 1));
          mbar_wait(bars + 8 * B_TL, 0);
          const uint32_t u = __float_as_uint(v.x);
          *(uint16_t*)(smem + OFF_T + t * 128 + ((t & 7) << 4)) = (uint16_t)u;
          *(uint16_t*)(smem + OFF_T + t * 128 + (((t & 7) ^ 1) << 4)) = (uint16_t)(u >> 16);
          asm volatile("fence.proxy.async.shared::cta;" ::: "memory");
          __syncwarp();
          mbar_arrive_if(lane == 0, bars + 8 * B_T);
        }
      }
    }
  } else {
    asm volatile("setmaxnreg.dec.sync.aligned.u32 24;");
    auto xf_load = [&](int q) {
      const uint32_t fb = bars + 8 * (B_FX + q);
      mbar_expect_tx(fb, U + 8192);
      tma3d(sb + q * U, &maps.x, fb, 64 * q, 0, 2 * rb);
      if (q >= 4) mbar_wait(bars + 8 * (B_FE + ((q - 4) >> 1)), 0);
      tma2d(sb + OFF_XB + (q & 3) * 8192, &maps.ft, fb, 64 * q, 64 * j);
    };
    if (elect_one()) {
      if (warp == 14) {
#pragma unroll
        for (int i = 0; i < B_FT; i++) mbar_init(bars + 8 * i, 1);
        asm volatile("fence.mbarrier_init.release.cluster;" ::: "memory");
        if (!helper) {
#pragma unroll 1
          for (int n = 0; n < 2; n++) {
            const uint32_t fb = bars + 8 * (B_FA + n);
            xf_load(2 * n); xf_load(2 * n + 1);
            mbar_expect_tx(fb, U);
            tma2d(sb + OFF_RING + n * U, &maps.g64, fb, f_full, 64 * n);
            tma2d(sb + OFF_RING + n * U + 8192, &maps.u64, fb, f_full, 64 * n);
          }
        }
      } else if (warp == 15) {
#pragma unroll
        for (int i = B_FT; i < NBAR; i++) mbar_init(bars + 8 * i, i < B_EA ? 1 : i < B_T ? 2 : 4);
#pragma unroll
        for (int i = 0; i < 8; i++) mbar_expect_tx(bars + 8 * (B_Z + i), U / 2);
        asm volatile("fence.mbarrier_init.release.cluster;" ::: "memory");
        asm volatile("fence.proxy.async.shared::cta;" ::: "memory");
      }
    }
    __syncwarp();
    asm volatile("bar.arrive 0, 384;" ::: "memory");
    asm volatile("bar.arrive 4, 256;" ::: "memory");
    __syncwarp();
    asm volatile("barrier.cluster.arrive.relaxed.aligned;" ::: "memory");
    asm volatile("bar.sync 3, 128;" ::: "memory");
    if (warp == 15 && !helper) {
        mbar_wait(bars + 8 * B_FE, 0);
        const uint32_t tag = (ld_x1(&ws->epoch[blockIdx.x * 8]) + 1) & 1;
        const int c = lane >> 4, jj = 16 * blockIdx.x + (lane & 15), jm = (2048 - jj) & 2047;
        const unsigned short* pr = (const unsigned short*)w_r + 256 * c;
        const unsigned short* pi = (const unsigned short*)w_i + 256 * c;
        const float wr = 0.25f * (bf_lo(__ldg(pr + jj * 257)) + bf_lo(__ldg(pr + jm * 257)));
        const float wi = 0.25f * (bf_lo(__ldg(pi + jj * 257)) - bf_lo(__ldg(pi + jm * 257)));
        st_u2(ws->Wh + c * 2048 + jj, c ? pack_bf16(-wi, wr) : pack_bf16(wr, wi), tag);
        __syncwarp();
        hint_add_if(lane == 0, &ws->cntW[0]);
        mbar_wait(bars + 8 * B_XS, 0);
        const uint32_t t0 = (uint32_t)clock();
        uint4 v;
        do { v = ld_x4(ws->gate + rb * 128 + 4 * lane); spin_guard(t0); } while (__any_sync(0xffffffffu, ((v.x ^ tag) | (v.y ^ tag) | (v.z ^ tag) | (v.w ^ tag)) & 1));
        *(uint4*)(smem + OFF_G + lane * 16) = v;
        __syncwarp();
        mbar_arrive_if(lane < 4, bars + 8 * B_G);
      }
    if ((!helper || warp == 15) && elect_one()) {
      if (warp < 14) {
        const int p = warp - 12;
#pragma unroll 1
        for (int i = 4 + p; i < 14; i += 2) asm volatile("prefetch.tensormap [%0];" ::"l"((const char*)&maps + i * 128) : "memory");
#pragma unroll 1
        for (int n = 2; n < 31; n++) {
          const bool table = n == 4 || n >= 29;
          const bool half = n >= 17 && n < 21;
          const int q = n < 4 ? n : n < 17 ? n - 1 : n - 5;
          const CUtensorMap* m = table ? &maps.e : half ? &maps.g32 + p : &maps.g64 + p;
          const int c0 = table ? 0 : half ? f_half : f_full + 64 * (q >> 3);
          const int c1 = table ? (2 * rb + ((n & 1) ^ 1)) * 128 + 64 * p : half ? 128 * (n - 17) : 64 * (q & 7);
          const uint32_t fb = bars + 8 * (B_FA + (n & 3)), dst = sb + OFF_RING + (n & 3) * U + p * 8192;
          if (n < 4) mbar_wait(bars + 8 * (B_FE + n - 2), 0);
          else mbar_wait(bars + 8 * (B_EA + (n & 3)), ((n >> 2) & 1) ^ 1);
          tma2d(dst, m, fb, c0, c1);
          if (p == 0) mbar_expect_tx(fb, U);
        }
      } else if (warp == 15) {
        const unsigned ep1 = ld_x1(&ws->epoch[blockIdx.x * 8]) + 1;
        flag_wait(&ws->cntX[helper ? 0 : 32 * j], ep1 * 16u);
        PROF_EV(22);
        mbar_expect_tx(bars + 8 * B_HX, U);
        bulk_load(sb + OFF_XB, ws->X + (size_t)(helper ? 128 : kg * 8 + tn) * 8192, U, bars + 8 * B_HX);
        if (!helper) {
          flag_wait(&ws->cntT[32 * j], ep1 * 64u);
          PROF_EV(23);
          mbar_expect_tx(bars + 8 * B_TL, U);
          tma3d(sb + OFF_T, &maps.t, bars + 8 * B_TL, 64 * j, 0, 2 * rb);
#pragma unroll 1
          for (int i = 0; i < 3; i++) {
            flag_wait(&ws->cntP[32 * (rb * 8 + j) + i], ep1 * 8u);
            mbar_wait(bars + 8 * (B_PZ + (i == 0)), 0);
            if (i == 2) PROF_EV(26);
            mbar_expect_tx(bars + 8 * (B_HP + i), U);
            bulk_load(sb + (i ? (i - 1) * U : OFF_T), ws->part + (size_t)((rb * 8 + j) * 3 + i) * 1024, U, bars + 8 * (B_HP + i));
          }
          ws->epoch[blockIdx.x * 8] = ep1;
        }
      } else {
#pragma unroll 1
        for (int q = 4; q < 8; q++) xf_load(q);
        mbar_wait(bars + 8 * (B_FE + 2), 0);
        mbar_expect_tx(bars + 8 * B_E0, U);
        tma2d(sb + OFF_XB, &maps.e, bars + 8 * B_E0, 0, 2 * rb * 128);
        tma2d(sb + OFF_XB + 8192, &maps.e, bars + 8 * B_E0, 0, 2 * rb * 128 + 64);
#pragma unroll 1
        for (int h2 = 0; h2 < 2; h2++) {
          const int s0 = 2 * rb + h2, sg = (s0 & ~6) | ((s0 & 2) << 1) | ((s0 & 4) >> 1);
          mbar_wait(bars + 8 * (B_XS + h2), 0);
#pragma unroll 1
          for (int c = 0; c < 2; c++) {
            asm volatile("cp.async.bulk.tensor.4d.global.shared::cta.bulk_group [%0, {%2, %3, %4, %5}], [%1];" ::"l"(&maps.xs),
                         "r"(sb + OFF_XB + h2 * 8192 + c * 4096), "r"(0), "r"(sg), "r"(0), "r"(16 * j + 8 * c) : "memory");
            if (j == 0)
              asm volatile("cp.async.bulk.global.shared::cta.bulk_group [%0], [%1], 256;" ::"l"(ws->X + 128 * 8192 + c * 4096 + sg * 128),
                           "r"(sb + OFF_SP + h2 * 512 + c * 256) : "memory");
            if (SPACE && h2 + c < 2) __nanosleep(SPACE);
          }
        }
        bulk_done_signal(&ws->cntX[32 * j]);
        PROF_EV(20);
        if (rb < 8) asm volatile("cp.async.bulk.prefetch.tensor.2d.L2.global [%0, {%1, %2}];" ::"l"(&maps.g32 + (rb >> 2)), "r"(f_half), "r"(128 * (rb & 3)) : "memory");
        else asm volatile("cp.async.bulk.prefetch.tensor.2d.L2.global [%0, {%1, %2}];" ::"l"(&maps.d224), "r"(64 * (rb - 8)), "r"(224 * j) : "memory");
#pragma unroll 1
        for (int t = 0; t < 8; t++) {
          const int i = t < 3 ? t + 1 : t < 6 ? t - 2 : 0;
          const int col = 64 * (2 * ((q4 + i) & 3) + ((t < 3 || t == 6) ? 1 - rank : rank));
          const uint32_t fb = bars + 8 * (B_FT + (t & 3)), dst = sb + (t & 3) * TB;
          mbar_wait(bars + 8 * (B_ET + (t == 2 ? 3 : t & 3)), t >> 2);
          mbar_expect_tx(fb, TB);
          tma2d(dst, &maps.d224, fb, col, 224 * j);
          if (t < 2) mbar_wait(bars + 8 * (B_ET + t + 1), 0);
          tma2d(dst + 28672, &maps.ft, fb, col, 64 * j);
        }
      }
    }
  }
}

typedef CUresult (*EncodeFn)(CUtensorMap*, CUtensorMapDataType, cuuint32_t, void*, const cuuint64_t*, const cuuint64_t*, const cuuint32_t*,
                             const cuuint32_t*, CUtensorMapInterleave, CUtensorMapSwizzle, CUtensorMapL2promotion, CUtensorMapFloatOOBfill);

static void encode(EncodeFn f, CUtensorMap* m, const void* base, int rank, const cuuint64_t* dims, const cuuint64_t* strides, const cuuint32_t* box,
                   CUtensorMapSwizzle sw) {
  cuuint32_t es[5] = {1, 1, 1, 1, 1};
  f(m, CU_TENSOR_MAP_DATA_TYPE_BFLOAT16, rank, (void*)base, dims, strides, box, es, CU_TENSOR_MAP_INTERLEAVE_NONE, sw,
    CU_TENSOR_MAP_L2_PROMOTION_L2_128B, CU_TENSOR_MAP_FLOAT_OOB_FILL_NONE);
}

extern "C" void kernel_launch(void* const* d_in, const int* in_sizes, int n_in, void* d_out, int out_size) {
  (void)in_sizes; (void)n_in; (void)out_size;
  const __nv_bfloat16* x = (const __nv_bfloat16*)d_in[0];
  const __nv_bfloat16* w_r = (const __nv_bfloat16*)d_in[1];
  const __nv_bfloat16* w_i = (const __nv_bfloat16*)d_in[2];
  const __nv_bfloat16* Wg = (const __nv_bfloat16*)d_in[4];
  const __nv_bfloat16* Wu = (const __nv_bfloat16*)d_in[5];
  const __nv_bfloat16* Wd = (const __nv_bfloat16*)d_in[6];
  const __nv_bfloat16* gw = (const __nv_bfloat16*)d_in[7];

  void* fp = nullptr; cudaDriverEntryPointQueryResult qr;
  cudaGetDriverEntryPoint("cuTensorMapEncodeTiled", &fp, cudaEnableDefault, &qr);
  EncodeFn enc = (EncodeFn)fp;
  void *pFT, *pET, *pDT, *pW;
  cudaGetSymbolAddress(&pDT, g_DT); cudaGetSymbolAddress(&pW, g_work);
  void *pX = ((Work*)pW)->X, *pT = ((Work*)pW)->T;
  cudaGetSymbolAddress(&pFT, g_FT); cudaGetSymbolAddress(&pET, g_ET);

  Maps mp;
  const CUtensorMapSwizzle S128 = CU_TENSOR_MAP_SWIZZLE_128B, S64 = CU_TENSOR_MAP_SWIZZLE_64B;
  { cuuint64_t d[3] = {512, 64, 32}, s[2] = {32768, 1024}; cuuint32_t b[3] = {64, 64, 2}, b2[3] = {64, 16, 1};
    encode(enc, &mp.x, x, 3, d, s, b, S128); encode(enc, &mp.o, d_out, 3, d, s, b2, S128); }
  { cuuint64_t d[2] = {512, 512}, s[1] = {1024}; cuuint32_t b[2] = {64, 64}; encode(enc, &mp.ft, pFT, 2, d, s, b, S128); }
  { cuuint64_t d[4] = {128, 32, 2, 129}, s[3] = {256, 8192, 16384}; cuuint32_t b[4] = {128, 1, 2, 8}; encode(enc, &mp.xs, pX, 4, d, s, b, CU_TENSOR_MAP_SWIZZLE_NONE); }
  { cuuint64_t d[3] = {512, 32, 64}, s[2] = {65536, 1024}; cuuint32_t b[3] = {32, 32, 2}; encode(enc, &mp.ts, pT, 3, d, s, b, S64); }
  { cuuint64_t d[3] = {512, 64, 32}, s[2] = {1024, 65536}; cuuint32_t b[3] = {64, 64, 2}; encode(enc, &mp.t, pT, 3, d, s, b, S128); }
  { cuuint64_t d[2] = {64, 4096}, s[1] = {128}; cuuint32_t b[2] = {64, 64}; encode(enc, &mp.e, pET, 2, d, s, b, S128); }
  { cuuint64_t d[2] = {1792, 512}, s[1] = {3584}; cuuint32_t b[2] = {64, 64}, b2[2] = {32, 128};
    encode(enc, &mp.g64, Wg, 2, d, s, b, S128); encode(enc, &mp.u64, Wu, 2, d, s, b, S128);
    encode(enc, &mp.g32, Wg, 2, d, s, b2, S64); encode(enc, &mp.u32, Wu, 2, d, s, b2, S64); }
  { cuuint64_t d[2] = {512, 1792}, s[1] = {1024}; cuuint32_t b[2] = {64, 224}; encode(enc, &mp.d224, Wd, 2, d, s, b, S128); }
  { cuuint64_t d[4] = {264, 32, 8, 8}, s[3] = {32896, 512, 4112}; cuuint32_t b[4] = {24, 32, 2, 1};
    encode(enc, &mp.wr, w_r, 4, d, s, b, CU_TENSOR_MAP_SWIZZLE_NONE); encode(enc, &mp.wi, w_i, 4, d, s, b, CU_TENSOR_MAP_SWIZZLE_NONE); }

  cudaFuncSetAttribute(fused_kernel, cudaFuncAttributeMaxDynamicSharedMemorySize, SMEM_BYTES);
  fused_kernel<<<NCTA, 512, SMEM_BYTES>>>((Work*)pW, (const uint16_t*)pDT, w_r, w_i, gw, x, mp);
}
```

```cpp
#include <cuda_runtime.h>
#include <cuda_bf16.h>
#include <cuda.h>
#include <stdint.h>

namespace tbl {
constexpr double PI = 3.14159265358979323846264338327950288;
constexpr double sin_s(double x) { double t = x, s = x; for (int n = 1; n < 12; n++) { t *= -x * x / ((2 * n) * (2 * n + 1)); s += t; } return s; }
constexpr double cos_s(double x) { double t = 1, s = 1; for (int n = 1; n < 12; n++) { t *= -x * x / ((2 * n - 1) * (2 * n)); s += t; } return s; }
constexpr double cos2048(int m) {
  m &= 2047; if (m > 1024) m = 2048 - m;
  bool neg = false; if (m > 512) { m = 1024 - m; neg = true; }
  double v = (m <= 256) ? cos_s(2 * PI * m / 2048) : sin_s(2 * PI * (512 - m) / 2048);
  return neg ? -v : v;
}
constexpr uint16_t to_bf16(double v) {
  if (v == 0) return 0;
  uint16_t s = 0; if (v < 0) { s = 0x8000; v = -v; }
  int e = 0; while (v >= 2) { v /= 2; e++; } while (v < 1) { v *= 2; e--; }
  double m = (v - 1) * 128; int mi = (int)m; double fr = m - mi;
  if (fr > 0.5 || (fr == 0.5 && (mi & 1))) mi++;
  if (mi == 128) { mi = 0; e++; }
  return (uint16_t)(s | ((e + 127) << 7) | mi);
}
struct CosT { uint16_t v[2048]; constexpr CosT() : v() { for (int i = 0; i < 2048; i++) v[i] = to_bf16(cos2048(i)); } };
struct alignas(1024) FT {
  uint16_t v[512 * 512];
  constexpr FT() : v() {
    CosT c;
    for (int r = 0; r < 512; r++) {
      int k = (r >> 4) * 8 + (r & 7), e = (r >> 3) & 1;
      int mul = 4 * k, add = e ? 512 : 0;
      if (k == 0 && e == 1) { mul = 1024; add = 0; }
      for (int d = 0; d < 512; d++) v[r * 512 + d] = c.v[(d * mul + add) & 2047];
    }
  }
};
struct alignas(1024) ET {
  uint16_t v[2048 * 128];
  constexpr ET() : v() {
    CosT c;
    for (int s = 0; s < 2048; s++)
      for (int j = 0; j < 64; j++) {
        const int o = (s & 31) * 8192 + (s >> 5) * 64 + j;
        v[o] = c.v[(s * j) & 2047]; v[o + 4096] = c.v[(s * j + 512) & 2047];
      }
  }
};
struct alignas(1024) DT {
  uint16_t v[64 * 64];
  constexpr DT() : v() {
    CosT c;
    for (int r = 0; r < 64; r++)
      for (int n = 0; n < 64; n++) {
        const int sg = r >> 1, s0 = (sg & ~6) | ((sg & 2) << 1) | ((sg & 4) >> 1), e = r & 1, f = n & 1;
        const int m = 64 * s0 * (n >> 1) + (e == f ? 0 : e ? -512 : 512);
        v[r * 64 + (((n >> 3) ^ (r & 7)) << 3) + (n & 7)] = c.v[m & 2047];
      }
  }
};
}

__device__ constexpr tbl::FT g_FT = tbl::FT();
__device__ constexpr tbl::ET g_ET = tbl::ET();
__device__ constexpr tbl::DT g_DT = tbl::DT();

struct alignas(1024) Work {
  unsigned epoch[132 * 8];
  unsigned cntX[8 * 32], cntT[8 * 32], cntP[128 * 32], cntW[32], cntH[32];
  alignas(16) float gate[16 * 128];
  alignas(16) uint2 Wh[2 * 2048];
  alignas(16) uint2 Ts[32 * 64];
  alignas(1024) uint16_t X[129 * 8192];
  alignas(1024) uint16_t T[32 * 64 * 512];
  alignas(1024) uint4 part[128 * 3 * 1024];
};
__device__ Work g_work;
#define PROF_EV(i) do {} while (0)
#define PROF_CK(i) do {} while (0)

__device__ __forceinline__ uint32_t smem_u32(const void* p) { return (uint32_t)__cvta_generic_to_shared(p); }
__device__ __forceinline__ void mbar_init(uint32_t bar, uint32_t cnt) { asm volatile("mbarrier.init.shared::cta.b64 [%0], %1;" ::"r"(bar), "r"(cnt)); }
__device__ __forceinline__ void mbar_expect_tx(uint32_t bar, uint32_t bytes) { asm volatile("mbarrier.arrive.expect_tx.shared::cta.b64 _, [%0], %1;" ::"r"(bar), "r"(bytes) : "memory"); }
__device__ __forceinline__ void mbar_arrive(uint32_t bar) { asm volatile("mbarrier.arrive.shared::cta.b64 _, [%0];" ::"r"(bar) : "memory"); }
__device__ __forceinline__ bool elect_one() {
  uint32_t p;
  asm volatile("{\n.reg .pred p;\nelect.sync _|p, 0xffffffff;\nselp.u32 %0, 1, 0, p;\n}" : "=r"(p));
  return p;
}
__device__ __forceinline__ void mbar_arrive_if(bool p, uint32_t bar) {
  asm volatile("{\n.reg .pred p;\nsetp.ne.b32 p, %1, 0;\n@p mbarrier.arrive.shared::cta.b64 _, [%0];\n}" ::"r"(bar), "r"((int)p) : "memory");
}
__device__ __forceinline__ void hint_add_if(bool p, unsigned* a) {
  asm volatile("{\n.reg .pred p;\nsetp.ne.b32 p, %1, 0;\n@p red.relaxed.gpu.global.add.u32 [%0], 1;\n}" ::"l"(a), "r"((int)p) : "memory");
}
__device__ __forceinline__ bool mbar_try(uint32_t bar, uint32_t parity) {
  uint32_t ok;
  asm volatile("{\n.reg .pred p;\nmbarrier.test_wait.parity.shared::cta.b64 p, [%1], %2;\nselp.u32 %0, 1, 0, p;\n}" : "=r"(ok) : "r"(bar), "r"(parity) : "memory");
  return ok;
}
__device__ __forceinline__ void mbar_wait(uint32_t bar, uint32_t parity) {
  asm volatile(
      "{\n.reg .pred p;\n.reg .u32 n;\nmov.u32 n, 0;\n"
      "W_LOOP:\nmbarrier.try_wait.parity.shared::cta.b64 p, [%0], %1;\n@p bra W_DONE;\n"
      "add.u32 n, n, 1;\nsetp.lt.u32 p, n, 0x40000;\n@p bra W_LOOP;\ntrap;\nW_DONE:\n}" ::"r"(bar), "r"(parity) : "memory");
}
__device__ __forceinline__ void bulk_load(uint32_t dst, const void* src, uint32_t bytes, uint32_t bar) {
  asm volatile("cp.async.bulk.shared::cluster.global.mbarrier::complete_tx::bytes [%0], [%1], %2, [%3];" ::"r"(dst), "l"(src), "r"(bytes), "r"(bar) : "memory");
}
__device__ __forceinline__ void spin_guard(uint32_t t0) { if ((uint32_t)clock() - t0 > (1u << 30)) __trap(); }
__device__ __forceinline__ float2 ld_x2(const float2* p) { float2 v; asm volatile("ld.relaxed.gpu.global.v2.f32 {%0,%1}, [%2];" : "=f"(v.x), "=f"(v.y) : "l"(p) : "memory"); return v; }
__device__ __forceinline__ void st_u2(uint2* p, uint32_t a, uint32_t b) { asm volatile("st.relaxed.gpu.global.v2.u32 [%0], {%1,%2};" ::"l"(p), "r"(a), "r"(b) : "memory"); }
__device__ __forceinline__ uint32_t ld_x1(const void* p) { uint32_t v; asm volatile("ld.relaxed.gpu.global.u32 %0, [%1];" : "=r"(v) : "l"(p) : "memory"); return v; }
__device__ __forceinline__ uint4 ld_x4(const void* p) { uint4 v; asm volatile("ld.relaxed.gpu.global.v4.u32 {%0,%1,%2,%3}, [%4];" : "=r"(v.x), "=r"(v.y), "=r"(v.z), "=r"(v.w) : "l"(p) : "memory"); return v; }
__device__ __forceinline__ uint32_t mapa(uint32_t a, uint32_t cta) { uint32_t r; asm volatile("mapa.shared::cluster.u32 %0, %1, %2;" : "=r"(r) : "r"(a), "r"(cta)); return r; }
__device__ __forceinline__ void stsm4t(uint32_t a, uint32_t r0, uint32_t r1, uint32_t r2, uint32_t r3) {
  asm volatile("stmatrix.sync.aligned.m8n8.x4.trans.shared.b16 [%0], {%1,%2,%3,%4};" ::"r"(a), "r"(r0), "r"(r1), "r"(r2), "r"(r3) : "memory");
}
__device__ __forceinline__ void hint_add(unsigned* p) { asm volatile("red.relaxed.gpu.global.add.u32 [%0], 1;" ::"l"(p) : "memory"); }
__device__ __forceinline__ void hint_wait(const unsigned* p, unsigned target) {
  const uint32_t t0 = (uint32_t)clock();
  while ((int)(ld_x1(p) - target) < 0) spin_guard(t0);
}
__device__ __forceinline__ void bulk_done_signal(unsigned* p) {
  asm volatile("cp.async.bulk.commit_group;\ncp.async.bulk.wait_group 0;\nfence.proxy.async.global;" ::: "memory");
  hint_add(p);
}
__device__ __forceinline__ void flag_wait(const unsigned* p, unsigned target) {
  hint_wait(p, target);
  asm volatile("fence.proxy.async.global;" ::: "memory");
}
__device__ __forceinline__ void tma2d(uint32_t dst, const CUtensorMap* m, uint32_t bar, int c0, int c1) {
  asm volatile("cp.async.bulk.tensor.2d.shared::cluster.global.mbarrier::complete_tx::bytes [%0], [%1, {%3, %4}], [%2];" ::"r"(dst), "l"(m), "r"(bar), "r"(c0), "r"(c1) : "memory");
}
__device__ __forceinline__ void tma3d(uint32_t dst, const CUtensorMap* m, uint32_t bar, int c0, int c1, int c2) {
  asm volatile("cp.async.bulk.tensor.3d.shared::cluster.global.mbarrier::complete_tx::bytes [%0], [%1, {%3, %4, %5}], [%2];" ::"r"(dst), "l"(m), "r"(bar), "r"(c0), "r"(c1), "r"(c2) : "memory");
}
__device__ __forceinline__ void tma4d(uint32_t dst, const CUtensorMap* m, uint32_t bar, int c0, int c1, int c2, int c3) {
  asm volatile("cp.async.bulk.tensor.4d.shared::cluster.global.mbarrier::complete_tx::bytes [%0], [%1, {%3, %4, %5, %6}], [%2];" ::"r"(dst), "l"(m), "r"(bar), "r"(c0), "r"(c1), "r"(c2), "r"(c3) : "memory");
}
__device__ __forceinline__ void wg_fence() { asm volatile("wgmma.fence.sync.aligned;" ::: "memory"); }
__device__ __forceinline__ void wg_commit() { asm volatile("wgmma.commit_group.sync.aligned;" ::: "memory"); }
template <int N> __device__ __forceinline__ void wg_wait() { asm volatile("wgmma.wait_group.sync.aligned %0;" ::"n"(N) : "memory"); }
template <int O, int N, int NN> __device__ __forceinline__ void fence_regs(float (&d)[NN]) {
#pragma unroll
  for (int i = 0; i < N; i++) asm volatile("" : "+f"(d[O + i])::"memory");
}
__device__ __forceinline__ uint32_t pack_bf16(float lo, float hi) {
  uint32_t r; asm("cvt.rn.bf16x2.f32 %0, %1, %2;" : "=r"(r) : "f"(hi), "f"(lo)); return r;
}
__device__ __forceinline__ uint32_t pack_pin(float lo, float hi) {
  uint32_t r; asm volatile("cvt.rn.bf16x2.f32 %0, %1, %2;" : "=r"(r) : "f"(hi), "f"(lo) : "memory"); return r;
}
__device__ __forceinline__ uint32_t add_bf2(uint32_t a, uint32_t b) { uint32_t r; asm("add.rn.bf16x2 %0, %1, %2;" : "=r"(r) : "r"(a), "r"(b)); return r; }
__device__ __forceinline__ float bf_lo(uint32_t u) { return __uint_as_float(u << 16); }
__device__ __forceinline__ float bf_hi(uint32_t u) { return __uint_as_float(u & 0xffff0000u); }

__device__ __forceinline__ uint64_t d128(uint32_t lo) { uint64_t d; asm("mov.b64 %0, {%1, 0x40000040};" : "=l"(d) : "r"(lo)); return d; }
__device__ __forceinline__ uint64_t d64(uint32_t lo) { uint64_t d; asm("mov.b64 %0, {%1, 0x80000020};" : "=l"(d) : "r"(lo)); return d; }
template<int O,int TB,int ACC,int NN> __device__ __forceinline__ void mma_ss64(float (&d)[NN], uint64_t da, uint64_t db, int sd = 0){
  if constexpr (ACC == 1) asm volatile("wgmma.mma_async.sync.aligned.m64n64k16.f32.bf16.bf16 {%0,%1,%2,%3,%4,%5,%6,%7,%8,%9,%10,%11,%12,%13,%14,%15,%16,%17,%18,%19,%20,%21,%22,%23,%24,%25,%26,%27,%28,%29,%30,%31}, %32, %33, 1, 1, 1, %35, %34;"
   : "+f"(d[O+0]), "+f"(d[O+1]), "+f"(d[O+2]), "+f"(d[O+3]), "+f"(d[O+4]), "+f"(d[O+5]), "+f"(d[O+6]), "+f"(d[O+7]), "+f"(d[O+8]), "+f"(d[O+9]), "+f"(d[O+10]), "+f"(d[O+11]), "+f"(d[O+12]), "+f"(d[O+13]), "+f"(d[O+14]), "+f"(d[O+15]), "+f"(d[O+16]), "+f"(d[O+17]), "+f"(d[O+18]), "+f"(d[O+19]), "+f"(d[O+20]), "+f"(d[O+21]), "+f"(d[O+22]), "+f"(d[O+23]), "+f"(d[O+24]), "+f"(d[O+25]), "+f"(d[O+26]), "+f"(d[O+27]), "+f"(d[O+28]), "+f"(d[O+29]), "+f"(d[O+30]), "+f"(d[O+31])
   : "l"(da), "l"(db), "n"(TB & 1), "n"(TB >> 1));
  else if constexpr (ACC == 0) asm volatile("wgmma.mma_async.sync.aligned.m64n64k16.f32.bf16.bf16 {%0,%1,%2,%3,%4,%5,%6,%7,%8,%9,%10,%11,%12,%13,%14,%15,%16,%17,%18,%19,%20,%21,%22,%23,%24,%25,%26,%27,%28,%29,%30,%31}, %32, %33, 0, 1, 1, %35, %34;"
   : "=f"(d[O+0]), "=f"(d[O+1]), "=f"(d[O+2]), "=f"(d[O+3]), "=f"(d[O+4]), "=f"(d[O+5]), "=f"(d[O+6]), "=f"(d[O+7]), "=f"(d[O+8]), "=f"(d[O+9]), "=f"(d[O+10]), "=f"(d[O+11]), "=f"(d[O+12]), "=f"(d[O+13]), "=f"(d[O+14]), "=f"(d[O+15]), "=f"(d[O+16]), "=f"(d[O+17]), "=f"(d[O+18]), "=f"(d[O+19]), "=f"(d[O+20]), "=f"(d[O+21]), "=f"(d[O+22]), "=f"(d[O+23]), "=f"(d[O+24]), "=f"(d[O+25]), "=f"(d[O+26]), "=f"(d[O+27]), "=f"(d[O+28]), "=f"(d[O+29]), "=f"(d[O+30]), "=f"(d[O+31])
   : "l"(da), "l"(db), "n"(TB & 1), "n"(TB >> 1));
  else asm volatile("{\n.reg .pred p;\nsetp.ne.b32 p, %36, 0;\nwgmma.mma_async.sync.aligned.m64n64k16.f32.bf16.bf16 {%0,%1,%2,%3,%4,%5,%6,%7,%8,%9,%10,%11,%12,%13,%14,%15,%16,%17,%18,%19,%20,%21,%22,%23,%24,%25,%26,%27,%28,%29,%30,%31}, %32, %33, p, 1, 1, %35, %34;\n}"
   : "+f"(d[O+0]), "+f"(d[O+1]), "+f"(d[O+2]), "+f"(d[O+3]), "+f"(d[O+4]), "+f"(d[O+5]), "+f"(d[O+6]), "+f"(d[O+7]), "+f"(d[O+8]), "+f"(d[O+9]), "+f"(d[O+10]), "+f"(d[O+11]), "+f"(d[O+12]), "+f"(d[O+13]), "+f"(d[O+14]), "+f"(d[O+15]), "+f"(d[O+16]), "+f"(d[O+17]), "+f"(d[O+18]), "+f"(d[O+19]), "+f"(d[O+20]), "+f"(d[O+21]), "+f"(d[O+22]), "+f"(d[O+23]), "+f"(d[O+24]), "+f"(d[O+25]), "+f"(d[O+26]), "+f"(d[O+27]), "+f"(d[O+28]), "+f"(d[O+29]), "+f"(d[O+30]), "+f"(d[O+31])
   : "l"(da), "l"(db), "n"(TB & 1), "n"(TB >> 1), "r"(sd));
}
template<int O,int TB,int ACC,int NN> __device__ __forceinline__ void mma_rs64(float (&d)[NN], uint32_t a0, uint32_t a1, uint32_t a2, uint32_t a3, uint64_t db, int sd = 0){
  if constexpr (ACC == 1) asm volatile("wgmma.mma_async.sync.aligned.m64n64k16.f32.bf16.bf16 {%0,%1,%2,%3,%4,%5,%6,%7,%8,%9,%10,%11,%12,%13,%14,%15,%16,%17,%18,%19,%20,%21,%22,%23,%24,%25,%26,%27,%28,%29,%30,%31}, {%32,%33,%34,%35}, %36, 1, 1, 1, %37;"
   : "+f"(d[O+0]), "+f"(d[O+1]), "+f"(d[O+2]), "+f"(d[O+3]), "+f"(d[O+4]), "+f"(d[O+5]), "+f"(d[O+6]), "+f"(d[O+7]), "+f"(d[O+8]), "+f"(d[O+9]), "+f"(d[O+10]), "+f"(d[O+11]), "+f"(d[O+12]), "+f"(d[O+13]), "+f"(d[O+14]), "+f"(d[O+15]), "+f"(d[O+16]), "+f"(d[O+17]), "+f"(d[O+18]), "+f"(d[O+19]), "+f"(d[O+20]), "+f"(d[O+21]), "+f"(d[O+22]), "+f"(d[O+23]), "+f"(d[O+24]), "+f"(d[O+25]), "+f"(d[O+26]), "+f"(d[O+27]), "+f"(d[O+28]), "+f"(d[O+29]), "+f"(d[O+30]), "+f"(d[O+31])
   : "r"(a0), "r"(a1), "r"(a2), "r"(a3), "l"(db), "n"(TB));
  else if constexpr (ACC == 0) asm volatile("wgmma.mma_async.sync.aligned.m64n64k16.f32.bf16.bf16 {%0,%1,%2,%3,%4,%5,%6,%7,%8,%9,%10,%11,%12,%13,%14,%15,%16,%17,%18,%19,%20,%21,%22,%23,%24,%25,%26,%27,%28,%29,%30,%31}, {%32,%33,%34,%35}, %36, 0, 1, 1, %37;"
   : "=f"(d[O+0]), "=f"(d[O+1]), "=f"(d[O+2]), "=f"(d[O+3]), "=f"(d[O+4]), "=f"(d[O+5]), "=f"(d[O+6]), "=f"(d[O+7]), "=f"(d[O+8]), "=f"(d[O+9]), "=f"(d[O+10]), "=f"(d[O+11]), "=f"(d[O+12]), "=f"(d[O+13]), "=f"(d[O+14]), "=f"(d[O+15]), "=f"(d[O+16]), "=f"(d[O+17]), "=f"(d[O+18]), "=f"(d[O+19]), "=f"(d[O+20]), "=f"(d[O+21]), "=f"(d[O+22]), "=f"(d[O+23]), "=f"(d[O+24]), "=f"(d[O+25]), "=f"(d[O+26]), "=f"(d[O+27]), "=f"(d[O+28]), "=f"(d[O+29]), "=f"(d[O+30]), "=f"(d[O+31])
   : "r"(a0), "r"(a1), "r"(a2), "r"(a3), "l"(db), "n"(TB));
  else asm volatile("{\n.reg .pred p;\nsetp.ne.b32 p, %38, 0;\nwgmma.mma_async.sync.aligned.m64n64k16.f32.bf16.bf16 {%0,%1,%2,%3,%4,%5,%6,%7,%8,%9,%10,%11,%12,%13,%14,%15,%16,%17,%18,%19,%20,%21,%22,%23,%24,%25,%26,%27,%28,%29,%30,%31}, {%32,%33,%34,%35}, %36, p, 1, 1, %37;\n}"
   : "+f"(d[O+0]), "+f"(d[O+1]), "+f"(d[O+2]), "+f"(d[O+3]), "+f"(d[O+4]), "+f"(d[O+5]), "+f"(d[O+6]), "+f"(d[O+7]), "+f"(d[O+8]), "+f"(d[O+9]), "+f"(d[O+10]), "+f"(d[O+11]), "+f"(d[O+12]), "+f"(d[O+13]), "+f"(d[O+14]), "+f"(d[O+15]), "+f"(d[O+16]), "+f"(d[O+17]), "+f"(d[O+18]), "+f"(d[O+19]), "+f"(d[O+20]), "+f"(d[O+21]), "+f"(d[O+22]), "+f"(d[O+23]), "+f"(d[O+24]), "+f"(d[O+25]), "+f"(d[O+26]), "+f"(d[O+27]), "+f"(d[O+28]), "+f"(d[O+29]), "+f"(d[O+30]), "+f"(d[O+31])
   : "r"(a0), "r"(a1), "r"(a2), "r"(a3), "l"(db), "n"(TB), "r"(sd));
}
template<int O,int TB,int ACC,int NN> __device__ __forceinline__ void mma_ss128(float (&d)[NN], uint64_t da, uint64_t db, int sd = 0){
  if constexpr (ACC == 1) asm volatile("wgmma.mma_async.sync.aligned.m64n128k16.f32.bf16.bf16 {%0,%1,%2,%3,%4,%5,%6,%7,%8,%9,%10,%11,%12,%13,%14,%15,%16,%17,%18,%19,%20,%21,%22,%23,%24,%25,%26,%27,%28,%29,%30,%31,%32,%33,%34,%35,%36,%37,%38,%39,%40,%41,%42,%43,%44,%45,%46,%47,%48,%49,%50,%51,%52,%53,%54,%55,%56,%57,%58,%59,%60,%61,%62,%63}, %64, %65, 1, 1, 1, %67, %66;"
   : "+f"(d[O+0]), "+f"(d[O+1]), "+f"(d[O+2]), "+f"(d[O+3]), "+f"(d[O+4]), "+f"(d[O+5]), "+f"(d[O+6]), "+f"(d[O+7]), "+f"(d[O+8]), "+f"(d[O+9]), "+f"(d[O+10]), "+f"(d[O+11]), "+f"(d[O+12]), "+f"(d[O+13]), "+f"(d[O+14]), "+f"(d[O+15]), "+f"(d[O+16]), "+f"(d[O+17]), "+f"(d[O+18]), "+f"(d[O+19]), "+f"(d[O+20]), "+f"(d[O+21]), "+f"(d[O+22]), "+f"(d[O+23]), "+f"(d[O+24]), "+f"(d[O+25]), "+f"(d[O+26]), "+f"(d[O+27]), "+f"(d[O+28]), "+f"(d[O+29]), "+f"(d[O+30]), "+f"(d[O+31]), "+f"(d[O+32]), "+f"(d[O+33]), "+f"(d[O+34]), "+f"(d[O+35]), "+f"(d[O+36]), "+f"(d[O+37]), "+f"(d[O+38]), "+f"(d[O+39]), "+f"(d[O+40]), "+f"(d[O+41]), "+f"(d[O+42]), "+f"(d[O+43]), "+f"(d[O+44]), "+f"(d[O+45]), "+f"(d[O+46]), "+f"(d[O+47]), "+f"(d[O+48]), "+f"(d[O+49]), "+f"(d[O+50]), "+f"(d[O+51]), "+f"(d[O+52]), "+f"(d[O+53]), "+f"(d[O+54]), "+f"(d[O+55]), "+f"(d[O+56]), "+f"(d[O+57]), "+f"(d[O+58]), "+f"(d[O+59]), "+f"(d[O+60]), "+f"(d[O+61]), "+f"(d[O+62]), "+f"(d[O+63])
   : "l"(da), "l"(db), "n"(TB & 1), "n"(TB >> 1));
  else if constexpr (ACC == 0) asm volatile("wgmma.mma_async.sync.aligned.m64n128k16.f32.bf16.bf16 {%0,%1,%2,%3,%4,%5,%6,%7,%8,%9,%10,%11,%12,%13,%14,%15,%16,%17,%18,%19,%20,%21,%22,%23,%24,%25,%26,%27,%28,%29,%30,%31,%32,%33,%34,%35,%36,%37,%38,%39,%40,%41,%42,%43,%44,%45,%46,%47,%48,%49,%50,%51,%52,%53,%54,%55,%56,%57,%58,%59,%60,%61,%62,%63}, %64, %65, 0, 1, 1, %67, %66;"
   : "=f"(d[O+0]), "=f"(d[O+1]), "=f"(d[O+2]), "=f"(d[O+3]), "=f"(d[O+4]), "=f"(d[O+5]), "=f"(d[O+6]), "=f"(d[O+7]), "=f"(d[O+8]), "=f"(d[O+9]), "=f"(d[O+10]), "=f"(d[O+11]), "=f"(d[O+12]), "=f"(d[O+13]), "=f"(d[O+14]), "=f"(d[O+15]), "=f"(d[O+16]), "=f"(d[O+17]), "=f"(d[O+18]), "=f"(d[O+19]), "=f"(d[O+20]), "=f"(d[O+21]), "=f"(d[O+22]), "=f"(d[O+23]), "=f"(d[O+24]), "=f"(d[O+25]), "=f"(d[O+26]), "=f"(d[O+27]), "=f"(d[O+28]), "=f"(d[O+29]), "=f"(d[O+30]), "=f"(d[O+31]), "=f"(d[O+32]), "=f"(d[O+33]), "=f"(d[O+34]), "=f"(d[O+35]), "=f"(d[O+36]), "=f"(d[O+37]), "=f"(d[O+38]), "=f"(d[O+39]), "=f"(d[O+40]), "=f"(d[O+41]), "=f"(d[O+42]), "=f"(d[O+43]), "=f"(d[O+44]), "=f"(d[O+45]), "=f"(d[O+46]), "=f"(d[O+47]), "=f"(d[O+48]), "=f"(d[O+49]), "=f"(d[O+50]), "=f"(d[O+51]), "=f"(d[O+52]), "=f"(d[O+53]), "=f"(d[O+54]), "=f"(d[O+55]), "=f"(d[O+56]), "=f"(d[O+57]), "=f"(d[O+58]), "=f"(d[O+59]), "=f"(d[O+60]), "=f"(d[O+61]), "=f"(d[O+62]), "=f"(d[O+63])
   : "l"(da), "l"(db), "n"(TB & 1), "n"(TB >> 1));
  else asm volatile("{\n.reg .pred p;\nsetp.ne.b32 p, %68, 0;\nwgmma.mma_async.sync.aligned.m64n128k16.f32.bf16.bf16 {%0,%1,%2,%3,%4,%5,%6,%7,%8,%9,%10,%11,%12,%13,%14,%15,%16,%17,%18,%19,%20,%21,%22,%23,%24,%25,%26,%27,%28,%29,%30,%31,%32,%33,%34,%35,%36,%37,%38,%39,%40,%41,%42,%43,%44,%45,%46,%47,%48,%49,%50,%51,%52,%53,%54,%55,%56,%57,%58,%59,%60,%61,%62,%63}, %64, %65, p, 1, 1, %67, %66;\n}"
   : "+f"(d[O+0]), "+f"(d[O+1]), "+f"(d[O+2]), "+f"(d[O+3]), "+f"(d[O+4]), "+f"(d[O+5]), "+f"(d[O+6]), "+f"(d[O+7]), "+f"(d[O+8]), "+f"(d[O+9]), "+f"(d[O+10]), "+f"(d[O+11]), "+f"(d[O+12]), "+f"(d[O+13]), "+f"(d[O+14]), "+f"(d[O+15]), "+f"(d[O+16]), "+f"(d[O+17]), "+f"(d[O+18]), "+f"(d[O+19]), "+f"(d[O+20]), "+f"(d[O+21]), "+f"(d[O+22]), "+f"(d[O+23]), "+f"(d[O+24]), "+f"(d[O+25]), "+f"(d[O+26]), "+f"(d[O+27]), "+f"(d[O+28]), "+f"(d[O+29]), "+f"(d[O+30]), "+f"(d[O+31]), "+f"(d[O+32]), "+f"(d[O+33]), "+f"(d[O+34]), "+f"(d[O+35]), "+f"(d[O+36]), "+f"(d[O+37]), "+f"(d[O+38]), "+f"(d[O+39]), "+f"(d[O+40]), "+f"(d[O+41]), "+f"(d[O+42]), "+f"(d[O+43]), "+f"(d[O+44]), "+f"(d[O+45]), "+f"(d[O+46]), "+f"(d[O+47]), "+f"(d[O+48]), "+f"(d[O+49]), "+f"(d[O+50]), "+f"(d[O+51]), "+f"(d[O+52]), "+f"(d[O+53]), "+f"(d[O+54]), "+f"(d[O+55]), "+f"(d[O+56]), "+f"(d[O+57]), "+f"(d[O+58]), "+f"(d[O+59]), "+f"(d[O+60]), "+f"(d[O+61]), "+f"(d[O+62]), "+f"(d[O+63])
   : "l"(da), "l"(db), "n"(TB & 1), "n"(TB >> 1), "r"(sd));
}
template<int O,int TB,int ACC,int NN> __device__ __forceinline__ void mma_rs128(float (&d)[NN], uint32_t a0, uint32_t a1, uint32_t a2, uint32_t a3, uint64_t db, int sd = 0){
  if constexpr (ACC == 1) asm volatile("wgmma.mma_async.sync.aligned.m64n128k16.f32.bf16.bf16 {%0,%1,%2,%3,%4,%5,%6,%7,%8,%9,%10,%11,%12,%13,%14,%15,%16,%17,%18,%19,%20,%21,%22,%23,%24,%25,%26,%27,%28,%29,%30,%31,%32,%33,%34,%35,%36,%37,%38,%39,%40,%41,%42,%43,%44,%45,%46,%47,%48,%49,%50,%51,%52,%53,%54,%55,%56,%57,%58,%59,%60,%61,%62,%63}, {%64,%65,%66,%67}, %68, 1, 1, 1, %69;"
   : "+f"(d[O+0]), "+f"(d[O+1]), "+f"(d[O+2]), "+f"(d[O+3]), "+f"(d[O+4]), "+f"(d[O+5]), "+f"(d[O+6]), "+f"(d[O+7]), "+f"(d[O+8]), "+f"(d[O+9]), "+f"(d[O+10]), "+f"(d[O+11]), "+f"(d[O+12]), "+f"(d[O+13]), "+f"(d[O+14]), "+f"(d[O+15]), "+f"(d[O+16]), "+f"(d[O+17]), "+f"(d[O+18]), "+f"(d[O+19]), "+f"(d[O+20]), "+f"(d[O+21]), "+f"(d[O+22]), "+f"(d[O+23]), "+f"(d[O+24]), "+f"(d[O+25]), "+f"(d[O+26]), "+f"(d[O+27]), "+f"(d[O+28]), "+f"(d[O+29]), "+f"(d[O+30]), "+f"(d[O+31]), "+f"(d[O+32]), "+f"(d[O+33]), "+f"(d[O+34]), "+f"(d[O+35]), "+f"(d[O+36]), "+f"(d[O+37]), "+f"(d[O+38]), "+f"(d[O+39]), "+f"(d[O+40]), "+f"(d[O+41]), "+f"(d[O+42]), "+f"(d[O+43]), "+f"(d[O+44]), "+f"(d[O+45]), "+f"(d[O+46]), "+f"(d[O+47]), "+f"(d[O+48]), "+f"(d[O+49]), "+f"(d[O+50]), "+f"(d[O+51]), "+f"(d[O+52]), "+f"(d[O+53]), "+f"(d[O+54]), "+f"(d[O+55]), "+f"(d[O+56]), "+f"(d[O+57]), "+f"(d[O+58]), "+f"(d[O+59]), "+f"(d[O+60]), "+f"(d[O+61]), "+f"(d[O+62]), "+f"(d[O+63])
   : "r"(a0), "r"(a1), "r"(a2), "r"(a3), "l"(db), "n"(TB));
  else if constexpr (ACC == 0) asm volatile("wgmma.mma_async.sync.aligned.m64n128k16.f32.bf16.bf16 {%0,%1,%2,%3,%4,%5,%6,%7,%8,%9,%10,%11,%12,%13,%14,%15,%16,%17,%18,%19,%20,%21,%22,%23,%24,%25,%26,%27,%28,%29,%30,%31,%32,%33,%34,%35,%36,%37,%38,%39,%40,%41,%42,%43,%44,%45,%46,%47,%48,%49,%50,%51,%52,%53,%54,%55,%56,%57,%58,%59,%60,%61,%62,%63}, {%64,%65,%66,%67}, %68, 0, 1, 1, %69;"
   : "=f"(d[O+0]), "=f"(d[O+1]), "=f"(d[O+2]), "=f"(d[O+3]), "=f"(d[O+4]), "=f"(d[O+5]), "=f"(d[O+6]), "=f"(d[O+7]), "=f"(d[O+8]), "=f"(d[O+9]), "=f"(d[O+10]), "=f"(d[O+11]), "=f"(d[O+12]), "=f"(d[O+13]), "=f"(d[O+14]), "=f"(d[O+15]), "=f"(d[O+16]), "=f"(d[O+17]), "=f"(d[O+18]), "=f"(d[O+19]), "=f"(d[O+20]), "=f"(d[O+21]), "=f"(d[O+22]), "=f"(d[O+23]), "=f"(d[O+24]), "=f"(d[O+25]), "=f"(d[O+26]), "=f"(d[O+27]), "=f"(d[O+28]), "=f"(d[O+29]), "=f"(d[O+30]), "=f"(d[O+31]), "=f"(d[O+32]), "=f"(d[O+33]), "=f"(d[O+34]), "=f"(d[O+35]), "=f"(d[O+36]), "=f"(d[O+37]), "=f"(d[O+38]), "=f"(d[O+39]), "=f"(d[O+40]), "=f"(d[O+41]), "=f"(d[O+42]), "=f"(d[O+43]), "=f"(d[O+44]), "=f"(d[O+45]), "=f"(d[O+46]), "=f"(d[O+47]), "=f"(d[O+48]), "=f"(d[O+49]), "=f"(d[O+50]), "=f"(d[O+51]), "=f"(d[O+52]), "=f"(d[O+53]), "=f"(d[O+54]), "=f"(d[O+55]), "=f"(d[O+56]), "=f"(d[O+57]), "=f"(d[O+58]), "=f"(d[O+59]), "=f"(d[O+60]), "=f"(d[O+61]), "=f"(d[O+62]), "=f"(d[O+63])
   : "r"(a0), "r"(a1), "r"(a2), "r"(a3), "l"(db), "n"(TB));
  else asm volatile("{\n.reg .pred p;\nsetp.ne.b32 p, %70, 0;\nwgmma.mma_async.sync.aligned.m64n128k16.f32.bf16.bf16 {%0,%1,%2,%3,%4,%5,%6,%7,%8,%9,%10,%11,%12,%13,%14,%15,%16,%17,%18,%19,%20,%21,%22,%23,%24,%25,%26,%27,%28,%29,%30,%31,%32,%33,%34,%35,%36,%37,%38,%39,%40,%41,%42,%43,%44,%45,%46,%47,%48,%49,%50,%51,%52,%53,%54,%55,%56,%57,%58,%59,%60,%61,%62,%63}, {%64,%65,%66,%67}, %68, p, 1, 1, %69;\n}"
   : "+f"(d[O+0]), "+f"(d[O+1]), "+f"(d[O+2]), "+f"(d[O+3]), "+f"(d[O+4]), "+f"(d[O+5]), "+f"(d[O+6]), "+f"(d[O+7]), "+f"(d[O+8]), "+f"(d[O+9]), "+f"(d[O+10]), "+f"(d[O+11]), "+f"(d[O+12]), "+f"(d[O+13]), "+f"(d[O+14]), "+f"(d[O+15]), "+f"(d[O+16]), "+f"(d[O+17]), "+f"(d[O+18]), "+f"(d[O+19]), "+f"(d[O+20]), "+f"(d[O+21]), "+f"(d[O+22]), "+f"(d[O+23]), "+f"(d[O+24]), "+f"(d[O+25]), "+f"(d[O+26]), "+f"(d[O+27]), "+f"(d[O+28]), "+f"(d[O+29]), "+f"(d[O+30]), "+f"(d[O+31]), "+f"(d[O+32]), "+f"(d[O+33]), "+f"(d[O+34]), "+f"(d[O+35]), "+f"(d[O+36]), "+f"(d[O+37]), "+f"(d[O+38]), "+f"(d[O+39]), "+f"(d[O+40]), "+f"(d[O+41]), "+f"(d[O+42]), "+f"(d[O+43]), "+f"(d[O+44]), "+f"(d[O+45]), "+f"(d[O+46]), "+f"(d[O+47]), "+f"(d[O+48]), "+f"(d[O+49]), "+f"(d[O+50]), "+f"(d[O+51]), "+f"(d[O+52]), "+f"(d[O+53]), "+f"(d[O+54]), "+f"(d[O+55]), "+f"(d[O+56]), "+f"(d[O+57]), "+f"(d[O+58]), "+f"(d[O+59]), "+f"(d[O+60]), "+f"(d[O+61]), "+f"(d[O+62]), "+f"(d[O+63])
   : "r"(a0), "r"(a1), "r"(a2), "r"(a3), "l"(db), "n"(TB), "r"(sd));
}

#define NEARLY 0
#define XAHEAD 3
#define HEADN 6
#define WBATCH 1
#define WB 8
#define WSLEEP 20
#define XSPREAD 4
#define NOSEND 0
#define MSPLIT 3
#define PFALL 1
#define L2PF 1
#define STAG 0
#define EPF 2
#define XNB 2
#define FNB 0
#define GNB 0
#define TH 5
#define PF0 4
#define FSPLIT 1
#define MGLU 1
#define SPC 2
#define TL 14
#define SPACE 40
#define WPF 1
#define WAFTER 7
#define WPACE 0
#define GATE_AT 4
#define TPACE 40
#define PFMODE 0
#define MAPMODE 1
template <int V> struct IC { static constexpr int value = V; };
struct Maps { CUtensorMap x, ft, g64, u64, e, wr, wi, xs, ts, t, g32, u32, d224, o; };

constexpr int NCTA = 130;
constexpr int U = 16384;
constexpr int TB = 36864;
constexpr int OFF_RING = 8 * U, OFF_Z = 12 * U, OFF_XB = 12 * U, OFF_T = 13 * U, OFF_D = OFF_T;
constexpr int OFF_BAR = 14 * U, OFF_SP = OFF_BAR + 512, OFF_G = OFF_SP + 1024 + 128;
constexpr int SMEM_BYTES = OFF_G + 512;
constexpr int B_FX = 0, B_FA = 8, B_FT = 12, B_Z = 16, B_W = 24, B_HX = 25, B_TL = 26, B_HP = 27, B_WR = 30, B_E0 = 34;
constexpr int B_EA = 35, B_ET = 39, B_PZ = 43, B_RDY = 45, B_FE = 46;
constexpr int B_T = 50, B_XS = 51, B_G = 53, B_RD0 = 54, NBAR = 55;
__host__ __device__ constexpr int rslot(int n) { return n & 3; }
__host__ __device__ constexpr int rpar(int n) { return (n >> 2) & 1; }

__global__ void __cluster_dims__(2, 1, 1) __launch_bounds__(512, 1)
fused_kernel(Work* __restrict__ ws, const uint16_t* __restrict__ dtab, const __nv_bfloat16* __restrict__ w_r, const __nv_bfloat16* __restrict__ w_i,
             const __nv_bfloat16* __restrict__ gate_w, const __nv_bfloat16* __restrict__ x, const __grid_constant__ Maps maps) {
  extern __shared__ __align__(1024) uint8_t smem[];
  if (threadIdx.x < 32 && elect_one()) {
#pragma unroll
    for (int i = 0; i < PF0; i++) asm volatile("prefetch.tensormap [%0];" ::"l"((const char*)&maps + i * 128) : "memory");
  }
  const uint32_t sb = smem_u32(smem);
  const uint32_t bars = sb + OFF_BAR;
  const int tid = threadIdx.x, lane = tid & 31;
  const int warp = __shfl_sync(0xffffffffu, tid >> 5, 0);
  const bool helper = blockIdx.x >= 128;
  const int cl = (blockIdx.x >> 1) & 63, rank = blockIdx.x & 1;
  const int q4 = (cl & 1) | ((cl >> 2) & 2), rb = ((cl >> 1) & 3) | ((cl >> 4) << 2);
  const int j = 2 * q4 + rank;
  const int f_full = 448 * q4 + (rank ? 256 : 0);
  const int f_half = 448 * q4 + (rank ? 224 : 192);
  const int kg = 2 * j + (rb >> 3), tn = rb & 7;

  if (tid == 64) { PROF_EV(0); PROF_CK(40); }
  if (warp < 8) {
    if (!helper && tid < 32) {
      const int r = 16 * j + (tid & 15);
      asm volatile("prefetch.global.L2 [%0];" ::"l"(x + (size_t)(2 * rb + (r >> 6) + 32 * (r & 63)) * 512 + 64 * (tid >> 4)));
    }
    asm volatile("barrier.cluster.arrive.relaxed.aligned;" ::: "memory");
    asm volatile("setmaxnreg.inc.sync.aligned.u32 192;");
    if (!helper) {
      const int wg = warp >> 2, w = warp & 3, g = lane >> 2;
      const bool elect = (tid & 127) == 0;
      float cX[32], cA[64], cB[64], cC[64], ci[64], ct[64];
      const int zero = blockIdx.x >> 16;
      uint32_t h[56], yf[16];
      const uint32_t d0 = (sb & 0x3FFFF) >> 4;
      const uint32_t dK = d0 | (1u << 16), dN = d0 | (512u << 16);
      const uint32_t dX = dK + wg * 512;
      constexpr uint32_t RING = OFF_RING >> 4;
      auto waitA = [&](int n) { mbar_wait(bars + 8 * (B_FA + rslot(n)), rpar(n)); };
      auto freeA = [&](int n) { mbar_arrive_if(elect, bars + 8 * (B_EA + rslot(n))); };
      auto nop = [] {};

      asm volatile("bar.sync 0, 384;" ::: "memory");
#pragma unroll 1
      for (int i = 0; i < 4; i++) {
        const uint64_t dx = d128(dX + i * 2048), df = d128(dK + (OFF_XB >> 4) + (i & 1) * 1024);
        mbar_wait(bars + 8 * (B_FX + 2 * i), 0);
        wg_fence();
        mma_ss64<0, 0, 2>(cX, df, dx, i);
        mma_ss64<0, 0, 1>(cX, df + 2, dx + 2);
        wg_commit(); wg_wait<1>();
        mbar_arrive_if(elect && i, bars + 8 * (B_EA + rslot(i - 1)));
        mma_ss64<0, 0, 1>(cX, df + 4, dx + 4);
        mma_ss64<0, 0, 1>(cX, df + 6, dx + 6);
        if (i == 0 && tid == 0) PROF_EV(1);
        mbar_wait(bars + 8 * (B_FX + 2 * i + 1), 0);
        wg_fence();
#pragma unroll
        for (int k = 0; k < 4; k++) mma_ss64<0, 0, 1>(cX, df + (512 + k * 2), dx + (1024 + k * 2));
        wg_commit();
        waitA(i);
        wg_fence();
        const uint64_t da = d128(dX + i * 1024), db = d128(dN + RING + i * 1024);
        mma_ss128<0, 1, 2>(cA, da, db, i);
        wg_commit(); wg_wait<1>();
        mbar_arrive_if(elect, bars + 8 * (B_FE + i));
#pragma unroll
        for (int k = 1; k < 4; k++) mma_ss128<0, 1, 1>(cA, da + k * 2, db + k * 128);
        wg_commit();
      }
      fence_regs<0, 32>(cX);
#pragma unroll
      for (int e = 0; e < 16; e++) yf[e] = pack_pin(cX[2 * e], cX[2 * e + 1]);
      if (tid == 0) { PROF_EV(2); PROF_CK(42); }
      {
        waitA(4); mbar_wait(bars + 8 * B_E0, 0);
        const uint64_t de = d128(dN + (wg ? RING : OFF_XB >> 4));
        wg_fence();
        mma_rs128<0, 1, 0>(cB, yf[0], yf[1], yf[2], yf[3], de);
        wg_commit();
        wg_wait<1>();
        freeA(3);
#pragma unroll
        for (int k = 1; k < 4; k++) mma_rs128<0, 1, 1>(cB, yf[4 * k], yf[4 * k + 1], yf[4 * k + 2], yf[4 * k + 3], de + k * 128);
        wg_commit();
      }
      bool rel = false;
      auto acquire = [&](int n) {
        rel = elect;
        if (!mbar_try(bars + 8 * (B_FA + rslot(n)), rpar(n))) { wg_wait<0>(); freeA(n - 1); rel = false; waitA(n); }
      };
      auto freeP = [&](int n) { mbar_arrive_if(rel, bars + 8 * (B_EA + rslot(n - 1))); };
      auto ffn_step = [&](auto first, auto split, float (&acc)[64], int n, int kb, auto done, auto work) {
        constexpr int SPLIT = decltype(split)::value;
        acquire(n);
        wg_fence();
        const uint64_t dx = d128(dX + kb * 1024), db = d128(dN + RING + rslot(n) * 1024);
        mma_ss128<0, 1, decltype(first)::value>(acc, dx, db, kb);
#pragma unroll
        for (int k = 1; k < SPLIT; k++) mma_ss128<0, 1, 1>(acc, dx + k * 2, db + k * 128);
        wg_commit();
        work();
        wg_wait<1>();
        freeP(n);
        done();
        if (SPLIT < 4) {
          wg_fence();
#pragma unroll
          for (int k = SPLIT; k < 4; k++) mma_ss128<0, 1, 1>(acc, dx + k * 2, db + k * 128);
          wg_commit();
        }
      };
      {
        const int s0 = 2 * rb + wg, kr = 2 * ((s0 & 1) | ((s0 & 4) >> 1));
        const int m = lane >> 3, r = lane & 7;
        const uint32_t a0 = sb + OFF_XB + wg * 8192 + (((w >> 1) * 8 + (m >> 1)) * 2 + (w & 1)) * 256 + (m & 1) * 128 + ((r ^ (kr + (m & 1))) << 4);
        ffn_step(IC<1>(), IC<4>(), cA, 5, 4, [&] { fence_regs<0, 64>(cB); }, nop);
        asm volatile("bar.sync 5, 256;" ::: "memory");
        auto stage = [&](int i) {
          stsm4t(a0 + i * 1024, pack_bf16(cB[8 * i] - cB[34 + 8 * i], cB[8 * i + 1] - cB[35 + 8 * i]),
                 pack_bf16(cB[32 + 8 * i] + cB[8 * i + 2], cB[33 + 8 * i] + cB[8 * i + 3]),
                 pack_bf16(cB[8 * i + 4] - cB[38 + 8 * i], cB[8 * i + 5] - cB[39 + 8 * i]),
                 pack_bf16(cB[36 + 8 * i] + cB[8 * i + 6], cB[37 + 8 * i] + cB[8 * i + 7]));
          if (j == 0 && w == 0) {
            const uint32_t a1 = r ? sb + OFF_SP + 1024 : sb + OFF_SP + wg * 512 + (m & 1) * 256 + (m >> 1) * 128;
#pragma unroll
            for (int n = 2 * i; n < 2 * i + 2; n++)
              asm volatile("stmatrix.sync.aligned.m8n8.x4.shared.b16 [%0], {%1,%2,%3,%4};" ::"r"(a1 + ((n ^ (kr + (m >> 1)) ^ r) << 4)),
                           "r"(pack_bf16(cB[4 * n], cB[4 * n + 1])), "r"(pack_bf16(cB[4 * n + 2], cB[4 * n + 3])),
                           "r"(pack_bf16(cB[32 + 4 * n], cB[33 + 4 * n])), "r"(pack_bf16(cB[34 + 4 * n], cB[35 + 4 * n])) : "memory");
          }
        };
        auto publish = [&] {
          asm volatile("fence.proxy.async.shared::cta;" ::: "memory");
          __syncwarp();
          mbar_arrive_if(lane == 0, bars + 8 * (B_XS + wg));
          if (tid == 0) PROF_EV(3);
        };
        stage(0);
        ffn_step(IC<1>(), IC<FSPLIT>(), cA, 6, 5, nop, nop);
        stage(1);
        ffn_step(IC<1>(), IC<FSPLIT>(), cA, 7, 6, nop, nop);
        stage(2);
        ffn_step(IC<1>(), IC<2>(), cA, 8, 7, [&] { stage(3); }, nop);
        publish();
      }
      float g0 = 0.f, g1 = 0.f;
      uint32_t tag = 0;
      uint32_t ob[2] = {0, 0};
      auto glu = [&](auto& acc, int half, int ho, int i0, int i1) {
#pragma unroll
        for (int i = i0; i < i1; i++)
          asm volatile("{\n.reg .b32 a, b;\ncvt.rn.relu.bf16x2.f32 a, %2, %1;\ncvt.rn.bf16x2.f32 b, %4, %3;\nmul.rn.bf16x2 a, a, b;\nmul.rn.bf16x2 %0, a, %5;\n}"
                       : "=r"(h[ho + i]) : "f"(acc[2 * i]), "f"(acc[2 * i + 1]), "f"(acc[half + 2 * i]), "f"(acc[half + 1 + 2 * i]), "r"(ob[i & 1]) : "memory");
      };
      ffn_step(IC<2>(), IC<1>(), cB, 9, zero, nop, nop);
#pragma unroll 1
      for (int kb = 1; kb < 8; kb++)
        ffn_step(IC<1>(), IC<FSPLIT>(), cB, 9 + kb, kb, nop, [&] {
          if (kb == 4 + 2 * wg) {
            mbar_wait(bars + 8 * B_G, 0);
            const uint32_t gb0 = *(const uint32_t*)(smem + OFF_G + (wg * 64 + w * 16 + g) * 4), gb1 = *(const uint32_t*)(smem + OFF_G + (wg * 64 + w * 16 + g + 8) * 4);
            tag = gb0 & 1; g0 = __uint_as_float(gb0 & ~1u); g1 = __uint_as_float(gb1 & ~1u);
            ob[0] = pack_bf16(1.0f - g0, 1.0f - g0); ob[1] = pack_bf16(1.0f - g1, 1.0f - g1);
            glu(cA, 32, 0, 0, 16);
          }
        });
      if (tid == 0) { PROF_EV(4); PROF_CK(43); }
      auto m_step = [&](auto first, int i) {
        acquire(17 + i);
        wg_fence();
        const uint64_t dx = d128(dX + i * 2048), dm = d64(dN + RING + rslot(17 + i) * 1024);
        mma_ss64<0, 1, decltype(first)::value>(ct, dx, dm);
#pragma unroll
        for (int k = 1; k < MSPLIT; k++) mma_ss64<0, 1, 1>(ct, dx + ((k >> 2) * 1024 + (k & 3) * 2), dm + k * 64);
        wg_commit();
        wg_wait<1>();
        freeP(17 + i);
        wg_fence();
#pragma unroll
        for (int k = MSPLIT; k < 8; k++) mma_ss64<0, 1, 1>(ct, dx + ((k >> 2) * 1024 + (k & 3) * 2), dm + k * 64);
        wg_commit();
      };
      m_step(IC<0>(), 0);
#pragma unroll 1
      for (int i = 1; i < 5; i++) {
        if (i == 1 + 2 * wg) glu(cB, 32, 16, 0, 16);
        if (i < 4) m_step(IC<1>(), i);
      }
      if (tid == 0) { PROF_EV(5); PROF_CK(44); }
      ffn_step(IC<0>(), IC<1>(), cC, 21, 0, nop, nop);
#pragma unroll 1
      for (int kb = 1; kb < 8; kb++)
        ffn_step(IC<1>(), IC<FSPLIT>(), cC, 21 + kb, kb, [&] { mbar_arrive_if(elect && !(kb & 1), bars + 8 * (B_ET + (kb >> 1) - 1)); }, [&] {
          if (kb == 1 + wg) glu(ct, 16, 48, 0, 8);
        });

      auto twait = [&](uint32_t bar, uint32_t par, int) { mbar_wait(bar, par); };
      const int fo = warp * 128 + lane;
      auto fetch = [&](uint4 (&pv)[4], int z) {
        twait(bars + 8 * (z < 4 ? B_Z + 2 * z + wg : B_HP + z - 4), 0, 8 + z);
        const uint8_t* src = smem + (z < 4 ? OFF_Z - z * U : z == 4 ? OFF_T : (z - 5) * U) + fo * 16;
#pragma unroll
        for (int i = 0; i < 4; i++) pv[i] = *(const uint4*)(src + i * 512);
      };
      auto check = [&](uint4 (&pv)[4], int z) {
        const uint32_t t0 = (uint32_t)clock();
        while (__any_sync(0xffffffffu, ((pv[0].x ^ tag) | (pv[1].x ^ tag) | (pv[2].x ^ tag) | (pv[3].x ^ tag)) & 1)) {
#pragma unroll
          for (int i = 0; i < 4; i++) pv[i] = ld_x4(ws->part + (size_t)((rb * 8 + j) * 3 + z - 4) * 1024 + fo + i * 32);
          spin_guard(t0);
        }
#pragma unroll
        for (int i = 0; i < 4; i++) pv[i].x &= ~1u;
      };
      const uint32_t peerZ = mapa(sb + OFF_Z + fo * 16, rank ^ 1), peerB = mapa(bars + 8 * (B_Z + wg), rank ^ 1);
      auto tile_mma = [&](auto off, int t, int k0, int k1, int init) {
        constexpr int O = decltype(off)::value;
        const uint64_t db = d128(dN + (t & 3) * (TB >> 4)), dw = db + rank * 256, dm = db + (rank ? 0 : 1536);
#pragma unroll
        for (int k = k0; k < k1; k++) {
          if (k == 0) mma_rs64<O, 1, 2>(ct, h[0], h[1], h[2], h[3], dw, init);
          else if (k < 14) mma_rs64<O, 1, 1>(ct, h[4 * k], h[4 * k + 1], h[4 * k + 2], h[4 * k + 3], k < 12 ? dw + k * 128 : dm + (k - 12) * 128);
          else mma_rs64<O, 1, 1>(ct, yf[4 * k - 56], yf[4 * k - 55], yf[4 * k - 54], yf[4 * k - 53], db + k * 128);
        }
      };
      uint4 pv[4] = {};
      auto tile = [&](auto off, int t) {
        constexpr int P = 32 - decltype(off)::value;
        const bool grid = t >= 4 && t < 7, pre = t >= 3 && t != 6;
        const int zo = grid ? t - 4 : t == 7 ? 3 : t - 1, z = t - 3;
        const int owner = rb * 8 + 2 * ((q4 + zo + 1) & 3) + rank;
        uint4* dst = ws->part + (size_t)(owner * 3 + zo) * 1024 + fo;
        const uint32_t src = sb + (z < 4 ? OFF_Z - z * U : OFF_T) + fo * 16;
        twait(bars + 8 * (B_FT + (t & 3)), t >> 2, t);
        wg_fence();
        tile_mma(off, t, 0, TH, zero);
        wg_commit();
        wg_wait<1>();
        mbar_arrive_if(elect && t < 6, bars + 8 * (B_ET + t - 1));
        if (t < 3) twait(bars + 8 * (t == 1 ? B_RD0 : B_RDY), 0, 14 + t);
        fence_regs<P, 32>(ct);
#pragma unroll
        for (int i = 0; i < 4; i++) {
          pv[i].x = (add_bf2(pv[i].x, pack_bf16(ct[P + 8 * i], ct[P + 8 * i + 1])) & ~(uint32_t)grid) | (tag & grid);
          pv[i].y = add_bf2(pv[i].y, pack_bf16(ct[P + 8 * i + 2], ct[P + 8 * i + 3]));
          pv[i].z = add_bf2(pv[i].z, pack_bf16(ct[P + 8 * i + 4], ct[P + 8 * i + 5]));
          pv[i].w = add_bf2(pv[i].w, pack_bf16(ct[P + 8 * i + 6], ct[P + 8 * i + 7]));
        }
        wg_fence();
#pragma unroll
        for (int i = 0; i < 4; i++) {
          asm volatile(
              "{\n.reg .pred p;\nsetp.ne.b32 p, %7, 0;\n@p st.relaxed.gpu.global.v4.u32 [%0], {%3,%4,%5,%6};\n"
              "@!p st.async.weak.shared::cluster.mbarrier::complete_tx::bytes.v4.b32 [%1], {%3,%4,%5,%6}, [%2];\n}" ::"l"(dst + i * 32),
              "r"(peerZ - zo * U + i * 512), "r"(peerB + 16 * zo), "r"(pv[i].x), "r"(pv[i].y), "r"(pv[i].z), "r"(pv[i].w), "r"((int)grid) : "memory");
          if (i == 3) hint_add_if(grid && lane == 0, &ws->cntP[32 * owner + zo]);
          tile_mma(off, t, TH + SPC * i, i < 3 ? TH + SPC * i + SPC : TL, 0);
        }
        wg_commit();
        if (pre) twait(bars + 8 * (z < 4 ? B_Z + 2 * z + wg : B_HP), 0, 8 + z);
        wg_fence();
#pragma unroll
        for (int i = 0; i < 4; i++) {
          asm volatile("{\n.reg .pred p;\nsetp.ne.b32 p, %5, 0;\nmov.b32 %0, 0;\nmov.b32 %1, 0;\nmov.b32 %2, 0;\nmov.b32 %3, 0;\n@p ld.shared.v4.u32 {%0,%1,%2,%3}, [%4];\n}"
                       : "=r"(pv[i].x), "=r"(pv[i].y), "=r"(pv[i].z), "=r"(pv[i].w) : "r"(src + i * 512), "r"((int)pre) : "memory");
          tile_mma(off, t, TL + i, i < 3 ? TL + 1 + i : 18, 0);
        }
        wg_commit();
      };
      asm volatile("barrier.cluster.wait.aligned;" ::: "memory");
      twait(bars + 8 * B_FT, 0, 0);
      wg_fence();
      tile_mma(IC<0>(), 0, 0, 5, zero);
      wg_commit();
      wg_wait<1>();
      mbar_arrive_if(elect, bars + 8 * (B_ET + 3));
      glu(cC, 32, 32, 0, 8);
      waitA(29 + wg);
      wg_fence();
      tile_mma(IC<0>(), 0, 5, 8, 0);
      tile_mma(IC<0>(), 0, 12, 14, 0);
      wg_commit();
      glu(cC, 32, 32, 8, 16);
      if (tid == 0) PROF_EV(6);
      if (tid == 128) PROF_EV(27);
      mbar_wait(bars + 8 * (j == 0 ? B_T : B_TL), 0);
      if (tid == 0) { PROF_EV(7); PROF_CK(45); }
      wg_fence();
      {
        const uint64_t dt = d128(dN + (OFF_T >> 4) + wg * 512), de = d128(dK + RING + (1 + wg) * 1024);
        mma_ss64<0, 1, 0>(ci, de, dt);
        mma_ss64<32, 1, 0>(ci, de + 512, dt);
#pragma unroll
        for (int k = 1; k < 4; k++) {
          mma_ss64<0, 1, 1>(ci, de + k * 2, dt + k * 128);
          mma_ss64<32, 1, 1>(ci, de + (512 + k * 2), dt + k * 128);
        }
        wg_commit();
      }
      tile_mma(IC<0>(), 0, 8, 12, 0);
      wg_commit();
      wg_wait<1>();
      if (elect) asm volatile("mbarrier.arrive.shared::cluster.b64 _, [%0];" ::"r"(mapa(bars + 8 * B_RDY, rank ^ 1)) : "memory");
      mbar_arrive_if(elect, bars + 8 * (B_PZ + 1));
      fence_regs<0, 64>(ci);
#pragma unroll
      for (int i = 0; i < 16; i++) {
        const float gg = ((i & 1) ? g1 : g0) * (2.0f / (2048.0f * 512.0f));
        if (i & 2) yf[i] = pack_pin((ci[2 * i] - ci[28 + 2 * i]) * gg, (ci[2 * i + 1] - ci[29 + 2 * i]) * gg);
        else yf[i] = pack_pin((ci[2 * i] + ci[36 + 2 * i]) * gg, (ci[2 * i + 1] + ci[37 + 2 * i]) * gg);
      }
      wg_fence();
      tile_mma(IC<0>(), 0, 14, 18, 0);
      wg_commit();
      if (tid == 0) PROF_EV(8);
      if (tid == 128) PROF_EV(28);
#pragma unroll 1
      for (int t = 1;; t += 2) {
        tile(IC<32>(), t);
        if (t == 7) break;
        tile(IC<0>(), t + 1);
      }
      if (tid == 0) { PROF_EV(9); PROF_CK(46); }
      if (tid == 128) PROF_EV(29);
      {
        uint4 p1[4], p2[4];
        auto acc4 = [&](uint4 (&d)[4], const uint4 (&a)[4]) {
#pragma unroll
          for (int i = 0; i < 4; i++) { d[i].x = add_bf2(d[i].x, a[i].x); d[i].y = add_bf2(d[i].y, a[i].y); d[i].z = add_bf2(d[i].z, a[i].z); d[i].w = add_bf2(d[i].w, a[i].w); }
        };
        fetch(p1, 5);
        check(pv, 4); check(p1, 5);
        acc4(pv, p1);
        fetch(p1, 3);
        if (tid == 0) PROF_EV(25);
        fetch(p2, 6);
        if (tid == 0) PROF_EV(24);
        check(p2, 6);
        acc4(p1, p2); acc4(pv, p1);
        const uint32_t ps[16] = {pv[0].x, pv[0].y, pv[0].z, pv[0].w, pv[1].x, pv[1].y, pv[1].z, pv[1].w, pv[2].x, pv[2].y, pv[2].z, pv[2].w, pv[3].x, pv[3].y, pv[3].z, pv[3].w};
        if (tid == 0) PROF_EV(14);
        wg_wait<0>();
        fence_regs<32, 32>(ct);
        float sum[32];
#pragma unroll
        for (int i = 0; i < 16; i++) { sum[2 * i] = ct[32 + 2 * i] + bf_lo(ps[i]); sum[2 * i + 1] = ct[33 + 2 * i] + bf_hi(ps[i]); }
        const uint32_t stg = sb + OFF_T + warp * 2048;
        const int mr = (lane & 7) + ((lane >> 3) & 1) * 8, mc = lane >> 4;
#pragma unroll
        for (int i = 0; i < 4; i++) {
          const uint32_t a = stg + mr * 128 + (((2 * i + mc) ^ (mr & 7)) << 4);
          asm volatile("stmatrix.sync.aligned.m8n8.x4.shared.b16 [%0], {%1,%2,%3,%4};" ::"r"(a), "r"(pack_bf16(sum[8 * i], sum[8 * i + 1])),
                       "r"(pack_bf16(sum[8 * i + 2], sum[8 * i + 3])), "r"(pack_bf16(sum[8 * i + 4], sum[8 * i + 5])),
                       "r"(pack_bf16(sum[8 * i + 6], sum[8 * i + 7])) : "memory");
        }
        asm volatile("fence.proxy.async.shared::cta;" ::: "memory");
        __syncwarp();
        if (elect_one()) {
          asm volatile("cp.async.bulk.tensor.3d.global.shared::cta.bulk_group [%0, {%2, %3, %4}], [%1];" ::"l"(&maps.o), "r"(stg), "r"(64 * j),
                       "r"(16 * w), "r"(2 * rb + wg) : "memory");
          asm volatile("cp.async.bulk.commit_group;\ncp.async.bulk.wait_group.read 0;" ::: "memory");
        }
      }
      if (tid == 0) { PROF_EV(15); PROF_CK(41); }
      if (tid == 128) PROF_EV(30);
    }
  } else if (warp < 12) {
    asm volatile("setmaxnreg.dec.sync.aligned.u32 104;");
    asm volatile("barrier.cluster.arrive.relaxed.aligned;" ::: "memory");
    const int t = tid - 256, w = warp - 8;
    const uint32_t ep = ld_x1(&ws->epoch[blockIdx.x * 8]);
    const uint32_t tag = (ep + 1) & 1;
    auto w_issue = [&](const CUtensorMap* m) {

      if (elect_one()) { mbar_expect_tx(bars + 8 * (B_WR + w), 3072); tma4d(sb + OFF_T + w * 3072, m, bars + 8 * (B_WR + w), 16 * kg, 0, 2 * w, tn); }

          __syncwarp();
    };
    auto gate_rows = [&] {
      const int r = 16 * j + 4 * w + (lane >> 3);
      const uint4* pg = (const uint4*)gate_w + (lane & 7);
      {
        float a = 0.f;
        asm volatile("bar.sync 4, 256;" ::: "memory");
#pragma unroll 1
        for (int hf = 0; hf < 2; hf++) {
          uint4 v[4], u[4];
#pragma unroll
          for (int kb = 0; kb < 4; kb++) v[kb] = __ldg(pg + (4 * hf + kb) * 8);
          mbar_wait(bars + 8 * (B_FE + 1 + 2 * hf), 0);
          if (hf) w_issue(&maps.wr);
#pragma unroll
          for (int kb = 0; kb < 4; kb++) u[kb] = *(const uint4*)(smem + (4 * hf + kb) * U + r * 128 + (((lane ^ r) & 7) << 4));
#pragma unroll
          for (int kb = 0; kb < 4; kb++) {
            const uint32_t uu[4] = {u[kb].x, u[kb].y, u[kb].z, u[kb].w}, vv[4] = {v[kb].x, v[kb].y, v[kb].z, v[kb].w};
#pragma unroll
            for (int e = 0; e < 4; e++) {
              uint32_t pr;
              asm("mul.rn.bf16x2 %0, %1, %2;" : "=r"(pr) : "r"(uu[e]), "r"(vv[e]));
              a += bf_lo(pr) + bf_hi(pr);
            }
          }
        }
#pragma unroll
        for (int o = 4; o; o >>= 1) a += __shfl_xor_sync(0xffffffffu, a, o);
        if ((lane & 7) == 0)
          asm volatile("st.relaxed.gpu.global.u32 [%0], %1;" ::"l"(ws->gate + rb * 128 + r),
                       "r"(pack_bf16(0.f, __fdividef(1.0f, 1.0f + __expf(-bf_lo(pack_bf16(a, 0.f))))) | tag) : "memory");
        if (t == 0) PROF_EV(18);
      }
    };
    {
      const int g = lane >> 2, q = lane & 3;
      uint32_t wf[32];
      if (!helper) {
        gate_rows();
        const uint32_t wa = sb + OFF_T + w * (3072 + 4) + q * 48 + g * 2;
#pragma unroll 1
        for (int ri = 0; ri < 2; ri++) {
          mbar_wait(bars + 8 * (B_WR + w), ri);
#pragma unroll
          for (int n2 = 0; n2 < 32 / WB; n2++) {
            uint32_t v[WB];
#pragma unroll
            for (int i = 0; i < WB; i++) {
              const int e = n2 * WB + i;
              asm volatile("ld.shared.u16 %0, [%1];" : "=r"(v[i]) : "r"(wa + ((e >> 1) & 7) * 192 + (e & 1) * (1536 + 2) + (e >> 4) * 16) : "memory");
            }
#pragma unroll
            for (int i = 0; i < WB; i++) wf[n2 * WB + i] = __byte_perm(wf[n2 * WB + i], v[i], 0x5432);
            if (WSLEEP) { asm volatile("nanosleep.u32 %0;" ::"r"(WSLEEP + (v[WB - 1] >> 16)) : "memory"); }
          }
          __syncwarp();
          if (ri == 0) w_issue(&maps.wi);
        }
        asm volatile("bar.sync 1, 128;" ::: "memory");
        if (t == 0) PROF_EV(11);
      } else {
        asm volatile("bar.sync 4, 256;" ::: "memory");
        hint_wait(&ws->cntW[0], (ep + 1) * 128u);
        const uint32_t t0 = (uint32_t)clock();
#pragma unroll 1
        for (;;) {
          uint32_t bad = 0;
#pragma unroll
          for (int i = 0; i < 32; i++) {
            const float2 v = ld_x2((const float2*)ws->Wh + (i >> 4) * 2048 + 16 * w + g + 8 * (i & 1) + 64 * q + ((i >> 1) & 7) * 256);
            wf[i] = __float_as_uint(v.x); bad |= __float_as_uint(v.y) ^ tag;
          }
          if (!__any_sync(0xffffffffu, bad & 1)) break;
          spin_guard(t0);
        }
        if (t == 0) PROF_EV(11);
      }
      if (w == 0 && elect_one()) { mbar_expect_tx(bars + 8 * B_W, 8192); bulk_load(sb + OFF_D, dtab, 8192, bars + 8 * B_W); }
      asm volatile("barrier.cluster.wait.aligned;" ::: "memory");
      mbar_wait(bars + 8 * B_W, 0);
      mbar_wait(bars + 8 * B_HX, 0);
      if (t == 0) PROF_EV(12);
      const uint32_t dd = (sb & 0x3FFFF) >> 4;
      const uint64_t dF = d128((dd + (OFF_D >> 4)) | (512u << 16)), dI = d128((dd + (OFF_D >> 4)) | (1u << 16)), dA = d128((dd + (OFF_XB >> 4)) | (512u << 16));
      float az[32];
      const int zero = blockIdx.x >> 16;
      uint32_t pf[32];
#pragma unroll
      for (int mt = 0; mt < 2; mt++) {
        wg_fence();
        if (mt == 0) mma_ss64<0, 3, 0>(az, dA, dF);
        else mma_ss64<0, 3, 2>(az, dA + 512, dF, zero);
#pragma unroll
        for (int k = 1; k < 4; k++) mma_ss64<0, 3, 1>(az, dA + (mt * 512 + k * 128), dF + k * 128);
        wg_commit();
        wg_wait<0>();
        fence_regs<0, 32>(az);
#pragma unroll
        for (int i = 0; i < 16; i++) {
          const float wr = bf_lo(wf[16 * mt + i]), wi = bf_hi(wf[16 * mt + i]);
          pf[16 * mt + i] = pack_pin(fmaf(az[2 * i], wr, -az[2 * i + 1] * wi), fmaf(az[2 * i], wi, az[2 * i + 1] * wr));
        }
      }
      if (t == 0) PROF_EV(16);
      {
        const int m = lane >> 3, r = lane & 7;
        const int sl = 2 * (m >> 1) + ((r >> 1) & 1) + 4 * (r >> 2);
        const uint32_t a0 = sb + OFF_XB + (2 * w + (m & 1)) * 2048 + sl * 64;
        uint32_t pk[16];
#pragma unroll
        for (int mt = 0; mt < 3; mt++) {
          if (mt < 2) {
            wg_fence();
            mma_rs64<0, 0, 2>(az, pf[16 * mt], pf[16 * mt + 1], pf[16 * mt + 2], pf[16 * mt + 3], dI, mt ? (int)helper : zero);
#pragma unroll
            for (int k = 1; k < 4; k++) mma_rs64<0, 0, 1>(az, pf[16 * mt + 4 * k], pf[16 * mt + 4 * k + 1], pf[16 * mt + 4 * k + 2], pf[16 * mt + 4 * k + 3], dI + k * 2);
            wg_commit();
          }
          if (mt > 0 && !helper) {
#pragma unroll
            for (int i = 0; i < 4; i++) stsm4t(a0 + ((((mt - 1) * 2 + (r & 1)) ^ (sl >> 1)) << 4) + i * 512, pk[4 * i], pk[4 * i + 1], pk[4 * i + 2], pk[4 * i + 3]);
          }
          if (mt < 2) {
            wg_wait<0>();
            fence_regs<0, 32>(az);
#pragma unroll
            for (int i = 0; i < 16; i++) pk[i] = pack_pin(az[2 * i], az[2 * i + 1]);
          }
        }
      }
      if (helper) {
#pragma unroll
        for (int i = 0; i < 16; i++) {
          const int n = i >> 1, s0 = 8 * (n >> 1) + 2 * (n & 1) + (q & 1) + 4 * (q >> 1);
          if ((n & 1) == (int)(blockIdx.x & 1)) st_u2(ws->Ts + s0 * 64 + 16 * w + g + 8 * (i & 1), pack_bf16(az[2 * i], az[2 * i + 1]), tag);
        }
        __syncwarp();
        hint_add_if(lane == 0, &ws->cntH[0]);
        if (t == 0) { ws->epoch[blockIdx.x * 8] = ep + 1; PROF_EV(13); }
      } else {
        asm volatile("fence.proxy.async.shared::cta;" ::: "memory");
        __syncwarp();
        if (elect_one()) {
          if (t == 0) PROF_EV(17);
          if (SPACE) __nanosleep(SPACE * w);
          asm volatile("cp.async.bulk.tensor.3d.global.shared::cta.bulk_group [%0, {%2, %3, %4}], [%1];" ::"l"(&maps.ts), "r"(sb + OFF_XB + w * 4096),
                       "r"(32 * kg), "r"(0), "r"(8 * tn + 2 * w) : "memory");
          bulk_done_signal(&ws->cntT[32 * j]);
          asm volatile("mbarrier.arrive.shared::cluster.b64 _, [%0];" ::"r"(mapa(bars + 8 * B_RD0, rank ^ 1)) : "memory");
          if (t == 96) PROF_EV(13);
        }
        __syncwarp();
        if (j == 0) {
          hint_wait(&ws->cntH[0], (ep + 1) * 8u);
          const uint32_t t0 = (uint32_t)clock();
          float2 v;
          do { v = ld_x2((const float2*)ws->Ts + 2 * rb * 64 + t); spin_guard(t0); } while (__any_sync(0xffffffffu, (__float_as_uint(v.y) ^ tag) & 1));
          mbar_wait(bars + 8 * B_TL, 0);
          const uint32_t u = __float_as_uint(v.x);
          *(uint16_t*)(smem + OFF_T + t * 128 + ((t & 7) << 4)) = (uint16_t)u;
          *(uint16_t*)(smem + OFF_T + t * 128 + (((t & 7) ^ 1) << 4)) = (uint16_t)(u >> 16);
          asm volatile("fence.proxy.async.shared::cta;" ::: "memory");
          __syncwarp();
          mbar_arrive_if(lane == 0, bars + 8 * B_T);
        }
      }
    }
  } else {
    asm volatile("setmaxnreg.dec.sync.aligned.u32 24;");
    auto xf_load = [&](int q) {
      const uint32_t fb = bars + 8 * (B_FX + q);
      mbar_expect_tx(fb, U + 8192);
      tma3d(sb + q * U, &maps.x, fb, 64 * q, 0, 2 * rb);
      if (q >= 4) mbar_wait(bars + 8 * (B_FE + ((q - 4) >> 1)), 0);
      tma2d(sb + OFF_XB + (q & 3) * 8192, &maps.ft, fb, 64 * q, 64 * j);
    };
    if (elect_one()) {
      if (warp == 14) {
#pragma unroll
        for (int i = 0; i < B_FT; i++) mbar_init(bars + 8 * i, 1);
        asm volatile("fence.mbarrier_init.release.cluster;" ::: "memory");
        if (!helper) {
#pragma unroll 1
          for (int n = 0; n < 2; n++) {
            const uint32_t fb = bars + 8 * (B_FA + n);
            xf_load(2 * n); xf_load(2 * n + 1);
            mbar_expect_tx(fb, U);
            tma2d(sb + OFF_RING + n * U, &maps.g64, fb, f_full, 64 * n);
            tma2d(sb + OFF_RING + n * U + 8192, &maps.u64, fb, f_full, 64 * n);
          }
        }
      } else if (warp == 15) {
#pragma unroll
        for (int i = B_FT; i < NBAR; i++) mbar_init(bars + 8 * i, i < B_EA ? 1 : i < B_T ? 2 : 4);
#pragma unroll
        for (int i = 0; i < 8; i++) mbar_expect_tx(bars + 8 * (B_Z + i), U / 2);
        asm volatile("fence.mbarrier_init.release.cluster;" ::: "memory");
        asm volatile("fence.proxy.async.shared::cta;" ::: "memory");
      }
    }
    __syncwarp();
    asm volatile("bar.arrive 0, 384;" ::: "memory");
    asm volatile("bar.arrive 4, 256;" ::: "memory");
    __syncwarp();
    asm volatile("barrier.cluster.arrive.relaxed.aligned;" ::: "memory");
    asm volatile("bar.sync 3, 128;" ::: "memory");
    if (warp == 15 && !helper) {
        mbar_wait(bars + 8 * B_FE, 0);
        const uint32_t tag = (ld_x1(&ws->epoch[blockIdx.x * 8]) + 1) & 1;
        const int c = lane >> 4, jj = 16 * blockIdx.x + (lane & 15), jm = (2048 - jj) & 2047;
        const unsigned short* pr = (const unsigned short*)w_r + 256 * c;
        const unsigned short* pi = (const unsigned short*)w_i + 256 * c;
        const float wr = 0.25f * (bf_lo(__ldg(pr + jj * 257)) + bf_lo(__ldg(pr + jm * 257)));
        const float wi = 0.25f * (bf_lo(__ldg(pi + jj * 257)) - bf_lo(__ldg(pi + jm * 257)));
        st_u2(ws->Wh + c * 2048 + jj, c ? pack_bf16(-wi, wr) : pack_bf16(wr, wi), tag);
        __syncwarp();
        hint_add_if(lane == 0, &ws->cntW[0]);
        mbar_wait(bars + 8 * B_XS, 0);
        const uint32_t t0 = (uint32_t)clock();
        uint4 v;
        do { v = ld_x4(ws->gate + rb * 128 + 4 * lane); spin_guard(t0); } while (__any_sync(0xffffffffu, ((v.x ^ tag) | (v.y ^ tag) | (v.z ^ tag) | (v.w ^ tag)) & 1));
        *(uint4*)(smem + OFF_G + lane * 16) = v;
        __syncwarp();
        mbar_arrive_if(lane < 4, bars + 8 * B_G);
      }
    if ((!helper || warp == 15) && elect_one()) {
      if (warp < 14) {
        const int p = warp - 12;
#pragma unroll 1
        for (int i = 4 + p; i < 14; i += 2) asm volatile("prefetch.tensormap [%0];" ::"l"((const char*)&maps + i * 128) : "memory");
#pragma unroll 1
        for (int n = 2; n < 31; n++) {
          const bool table = n == 4 || n >= 29;
          const bool half = n >= 17 && n < 21;
          const int q = n < 4 ? n : n < 17 ? n - 1 : n - 5;
          const CUtensorMap* m = table ? &maps.e : half ? &maps.g32 + p : &maps.g64 + p;
          const int c0 = table ? 0 : half ? f_half : f_full + 64 * (q >> 3);
          const int c1 = table ? (2 * rb + ((n & 1) ^ 1)) * 128 + 64 * p : half ? 128 * (n - 17) : 64 * (q & 7);
          const uint32_t fb = bars + 8 * (B_FA + (n & 3)), dst = sb + OFF_RING + (n & 3) * U + p * 8192;
          if (n < 4) mbar_wait(bars + 8 * (B_FE + n - 2), 0);
          else mbar_wait(bars + 8 * (B_EA + (n & 3)), ((n >> 2) & 1) ^ 1);
          tma2d(dst, m, fb, c0, c1);
          if (p == 0) mbar_expect_tx(fb, U);
        }
      } else if (warp == 15) {
        const unsigned ep1 = ld_x1(&ws->epoch[blockIdx.x * 8]) + 1;
        flag_wait(&ws->cntX[helper ? 0 : 32 * j], ep1 * 16u);
        PROF_EV(22);
        mbar_expect_tx(bars + 8 * B_HX, U);
        bulk_load(sb + OFF_XB, ws->X + (size_t)(helper ? 128 : kg * 8 + tn) * 8192, U, bars + 8 * B_HX);
        if (!helper) {
          flag_wait(&ws->cntT[32 * j], ep1 * 64u);
          PROF_EV(23);
          mbar_expect_tx(bars + 8 * B_TL, U);
          tma3d(sb + OFF_T, &maps.t, bars + 8 * B_TL, 64 * j, 0, 2 * rb);
#pragma unroll 1
          for (int i = 0; i < 3; i++) {
            flag_wait(&ws->cntP[32 * (rb * 8 + j) + i], ep1 * 8u);
            mbar_wait(bars + 8 * (B_PZ + (i == 0)), 0);
            if (i == 2) PROF_EV(26);
            mbar_expect_tx(bars + 8 * (B_HP + i), U);
            bulk_load(sb + (i ? (i - 1) * U : OFF_T), ws->part + (size_t)((rb * 8 + j) * 3 + i) * 1024, U, bars + 8 * (B_HP + i));
          }
          ws->epoch[blockIdx.x * 8] = ep1;
        }
      } else {
#pragma unroll 1
        for (int q = 4; q < 8; q++) xf_load(q);
        mbar_wait(bars + 8 * (B_FE + 2), 0);
        mbar_expect_tx(bars + 8 * B_E0, U);
        tma2d(sb + OFF_XB, &maps.e, bars + 8 * B_E0, 0, 2 * rb * 128);
        tma2d(sb + OFF_XB + 8192, &maps.e, bars + 8 * B_E0, 0, 2 * rb * 128 + 64);
#pragma unroll 1
        for (int h2 = 0; h2 < 2; h2++) {
          const int s0 = 2 * rb + h2, sg = (s0 & ~6) | ((s0 & 2) << 1) | ((s0 & 4) >> 1);
          mbar_wait(bars + 8 * (B_XS + h2), 0);
#pragma unroll 1
          for (int c = 0; c < 2; c++) {
            asm volatile("cp.async.bulk.tensor.4d.global.shared::cta.bulk_group [%0, {%2, %3, %4, %5}], [%1];" ::"l"(&maps.xs),
                         "r"(sb + OFF_XB + h2 * 8192 + c * 4096), "r"(0), "r"(sg), "r"(0), "r"(16 * j + 8 * c) : "memory");
            if (j == 0)
              asm volatile("cp.async.bulk.global.shared::cta.bulk_group [%0], [%1], 256;" ::"l"(ws->X + 128 * 8192 + c * 4096 + sg * 128),
                           "r"(sb + OFF_SP + h2 * 512 + c * 256) : "memory");
            if (SPACE && h2 + c < 2) __nanosleep(SPACE);
          }
        }
        bulk_done_signal(&ws->cntX[32 * j]);
        PROF_EV(20);
        if (rb < 8) asm volatile("cp.async.bulk.prefetch.tensor.2d.L2.global [%0, {%1, %2}];" ::"l"(&maps.g32 + (rb >> 2)), "r"(f_half), "r"(128 * (rb & 3)) : "memory");
        else asm volatile("cp.async.bulk.prefetch.tensor.2d.L2.global [%0, {%1, %2}];" ::"l"(&maps.d224), "r"(64 * (rb - 8)), "r"(224 * j) : "memory");
#pragma unroll 1
        for (int t = 0; t < 8; t++) {
          const int i = t < 3 ? t + 1 : t < 6 ? t - 2 : 0;
          const int col = 64 * (2 * ((q4 + i) & 3) + ((t < 3 || t == 6) ? 1 - rank : rank));
          const uint32_t fb = bars + 8 * (B_FT + (t & 3)), dst = sb + (t & 3) * TB;
          mbar_wait(bars + 8 * (B_ET + (t == 2 ? 3 : t & 3)), t >> 2);
          mbar_expect_tx(fb, TB);
          tma2d(dst, &maps.d224, fb, col, 224 * j);
          if (t < 2) mbar_wait(bars + 8 * (B_ET + t + 1), 0);
          tma2d(dst + 28672, &maps.ft, fb, col, 64 * j);
        }
      }
    }
  }
}

typedef CUresult (*EncodeFn)(CUtensorMap*, CUtensorMapDataType, cuuint32_t, void*, const cuuint64_t*, const cuuint64_t*, const cuuint32_t*,
                             const cuuint32_t*, CUtensorMapInterleave, CUtensorMapSwizzle, CUtensorMapL2promotion, CUtensorMapFloatOOBfill);

static void encode(EncodeFn f, CUtensorMap* m, const void* base, int rank, const cuuint64_t* dims, const cuuint64_t* strides, const cuuint32_t* box,
                   CUtensorMapSwizzle sw) {
  cuuint32_t es[5] = {1, 1, 1, 1, 1};
  f(m, CU_TENSOR_MAP_DATA_TYPE_BFLOAT16, rank, (void*)base, dims, strides, box, es, CU_TENSOR_MAP_INTERLEAVE_NONE, sw,
    CU_TENSOR_MAP_L2_PROMOTION_L2_128B, CU_TENSOR_MAP_FLOAT_OOB_FILL_NONE);
}

extern "C" void kernel_launch(void* const* d_in, const int* in_sizes, int n_in, void* d_out, int out_size) {
  (void)in_sizes; (void)n_in; (void)out_size;
  const __nv_bfloat16* x = (const __nv_bfloat16*)d_in[0];
  const __nv_bfloat16* w_r = (const __nv_bfloat16*)d_in[1];
  const __nv_bfloat16* w_i = (const __nv_bfloat16*)d_in[2];
  const __nv_bfloat16* Wg = (const __nv_bfloat16*)d_in[4];
  const __nv_bfloat16* Wu = (const __nv_bfloat16*)d_in[5];
  const __nv_bfloat16* Wd = (const __nv_bfloat16*)d_in[6];
  const __nv_bfloat16* gw = (const __nv_bfloat16*)d_in[7];

  void* fp = nullptr; cudaDriverEntryPointQueryResult qr;
  cudaGetDriverEntryPoint("cuTensorMapEncodeTiled", &fp, cudaEnableDefault, &qr);
  EncodeFn enc = (EncodeFn)fp;
  void *pFT, *pET, *pDT, *pW;
  cudaGetSymbolAddress(&pDT, g_DT); cudaGetSymbolAddress(&pW, g_work);
  void *pX = ((Work*)pW)->X, *pT = ((Work*)pW)->T;
  cudaGetSymbolAddress(&pFT, g_FT); cudaGetSymbolAddress(&pET, g_ET);

  Maps mp;
  const CUtensorMapSwizzle S128 = CU_TENSOR_MAP_SWIZZLE_128B, S64 = CU_TENSOR_MAP_SWIZZLE_64B;
  { cuuint64_t d[3] = {512, 64, 32}, s[2] = {32768, 1024}; cuuint32_t b[3] = {64, 64, 2}, b2[3] = {64, 16, 1};
    encode(enc, &mp.x, x, 3, d, s, b, S128); encode(enc, &mp.o, d_out, 3, d, s, b2, S128); }
  { cuuint64_t d[2] = {512, 512}, s[1] = {1024}; cuuint32_t b[2] = {64, 64}; encode(enc, &mp.ft, pFT, 2, d, s, b, S128); }
  { cuuint64_t d[4] = {128, 32, 2, 129}, s[3] = {256, 8192, 16384}; cuuint32_t b[4] = {128, 1, 2, 8}; encode(enc, &mp.xs, pX, 4, d, s, b, CU_TENSOR_MAP_SWIZZLE_NONE); }
  { cuuint64_t d[3] = {512, 32, 64}, s[2] = {65536, 1024}; cuuint32_t b[3] = {32, 32, 2}; encode(enc, &mp.ts, pT, 3, d, s, b, S64); }
  { cuuint64_t d[3] = {512, 64, 32}, s[2] = {1024, 65536}; cuuint32_t b[3] = {64, 64, 2}; encode(enc, &mp.t, pT, 3, d, s, b, S128); }
  { cuuint64_t d[2] = {64, 4096}, s[1] = {128}; cuuint32_t b[2] = {64, 64}; encode(enc, &mp.e, pET, 2, d, s, b, S128); }
  { cuuint64_t d[2] = {1792, 512}, s[1] = {3584}; cuuint32_t b[2] = {64, 64}, b2[2] = {32, 128};
    encode(enc, &mp.g64, Wg, 2, d, s, b, S128); encode(enc, &mp.u64, Wu, 2, d, s, b, S128);
    encode(enc, &mp.g32, Wg, 2, d, s, b2, S64); encode(enc, &mp.u32, Wu, 2, d, s, b2, S64); }
  { cuuint64_t d[2] = {512, 1792}, s[1] = {1024}; cuuint32_t b[2] = {64, 224}; encode(enc, &mp.d224, Wd, 2, d, s, b, S128); }
  { cuuint64_t d[4] = {264, 32, 8, 8}, s[3] = {32896, 512, 4112}; cuuint32_t b[4] = {24, 32, 2, 1};
    encode(enc, &mp.wr, w_r, 4, d, s, b, CU_TENSOR_MAP_SWIZZLE_NONE); encode(enc, &mp.wi, w_i, 4, d, s, b, CU_TENSOR_MAP_SWIZZLE_NONE); }

  cudaFuncSetAttribute(fused_kernel, cudaFuncAttributeMaxDynamicSharedMemorySize, SMEM_BYTES);
  fused_kernel<<<NCTA, 512, SMEM_BYTES>>>((Work*)pW, (const uint16_t*)pDT, w_r, w_i, gw, x, mp);
}
```

```cpp
#include <cuda_runtime.h>
#include <cuda_bf16.h>
#include <cuda.h>
#include <stdint.h>

namespace tbl {
constexpr double PI = 3.14159265358979323846264338327950288;
constexpr double sin_s(double x) { double t = x, s = x; for (int n = 1; n < 12; n++) { t *= -x * x / ((2 * n) * (2 * n + 1)); s += t; } return s; }
constexpr double cos_s(double x) { double t = 1, s = 1; for (int n = 1; n < 12; n++) { t *= -x * x / ((2 * n - 1) * (2 * n)); s += t; } return s; }
constexpr double cos2048(int m) {
  m &= 2047; if (m > 1024) m = 2048 - m;
  bool neg = false; if (m > 512) { m = 1024 - m; neg = true; }
  double v = (m <= 256) ? cos_s(2 * PI * m / 2048) : sin_s(2 * PI * (512 - m) / 2048);
  return neg ? -v : v;
}
constexpr uint16_t to_bf16(double v) {
  if (v == 0) return 0;
  uint16_t s = 0; if (v < 0) { s = 0x8000; v = -v; }
  int e = 0; while (v >= 2) { v /= 2; e++; } while (v < 1) { v *= 2; e--; }
  double m = (v - 1) * 128; int mi = (int)m; double fr = m - mi;
  if (fr > 0.5 || (fr == 0.5 && (mi & 1))) mi++;
  if (mi == 128) { mi = 0; e++; }
  return (uint16_t)(s | ((e + 127) << 7) | mi);
}
struct CosT { uint16_t v[2048]; constexpr CosT() : v() { for (int i = 0; i < 2048; i++) v[i] = to_bf16(cos2048(i)); } };
struct alignas(1024) FT {
  uint16_t v[512 * 512];
  constexpr FT() : v() {
    CosT c;
    for (int r = 0; r < 512; r++) {
      int k = (r >> 4) * 8 + (r & 7), e = (r >> 3) & 1;
      int mul = 4 * k, add = e ? 512 : 0;
      if (k == 0 && e == 1) { mul = 1024; add = 0; }
      for (int d = 0; d < 512; d++) v[r * 512 + d] = c.v[(d * mul + add) & 2047];
    }
  }
};
struct alignas(1024) ET {
  uint16_t v[2048 * 128];
  constexpr ET() : v() {
    CosT c;
    for (int s = 0; s < 2048; s++)
      for (int j = 0; j < 64; j++) {
        const int o = (s & 31) * 8192 + (s >> 5) * 64 + j;
        v[o] = c.v[(s * j) & 2047]; v[o + 4096] = c.v[(s * j + 512) & 2047];
      }
  }
};
struct alignas(1024) DT {
  uint16_t v[64 * 64];
  constexpr DT() : v() {
    CosT c;
    for (int r = 0; r < 64; r++)
      for (int n = 0; n < 64; n++) {
        const int sg = r >> 1, s0 = (sg & ~6) | ((sg & 2) << 1) | ((sg & 4) >> 1), e = r & 1, f = n & 1;
        const int m = 64 * s0 * (n >> 1) + (e == f ? 0 : e ? -512 : 512);
        v[r * 64 + (((n >> 3) ^ (r & 7)) << 3) + (n & 7)] = c.v[m & 2047];
      }
  }
};
}

__device__ constexpr tbl::FT g_FT = tbl::FT();
__device__ constexpr tbl::ET g_ET = tbl::ET();
__device__ constexpr tbl::DT g_DT = tbl::DT();

struct alignas(1024) Work {
  unsigned epoch[132 * 8];
  unsigned cntX[8 * 32], cntT[8 * 32], cntP[128 * 32], cntW[32], cntH[32];
  alignas(16) float gate[16 * 128];
  alignas(16) uint2 Wh[2 * 2048];
  alignas(16) uint2 Ts[32 * 64];
  alignas(1024) uint16_t X[129 * 8192];
  alignas(1024) uint16_t T[32 * 64 * 512];
  alignas(1024) uint4 part[128 * 3 * 1024];
};
__device__ Work g_work;
#define PROF_EV(i) do {} while (0)
#define PROF_CK(i) do {} while (0)

__device__ __forceinline__ uint32_t smem_u32(const void* p) { return (uint32_t)__cvta_generic_to_shared(p); }
__device__ __forceinline__ void mbar_init(uint32_t bar, uint32_t cnt) { asm volatile("mbarrier.init.shared::cta.b64 [%0], %1;" ::"r"(bar), "r"(cnt)); }
__device__ __forceinline__ void mbar_expect_tx(uint32_t bar, uint32_t bytes) { asm volatile("mbarrier.arrive.expect_tx.shared::cta.b64 _, [%0], %1;" ::"r"(bar), "r"(bytes) : "memory"); }
__device__ __forceinline__ void mbar_arrive(uint32_t bar) { asm volatile("mbarrier.arrive.shared::cta.b64 _, [%0];" ::"r"(bar) : "memory"); }
__device__ __forceinline__ bool elect_one() {
  uint32_t p;
  asm volatile("{\n.reg .pred p;\nelect.sync _|p, 0xffffffff;\nselp.u32 %0, 1, 0, p;\n}" : "=r"(p));
  return p;
}
__device__ __forceinline__ void mbar_arrive_if(bool p, uint32_t bar) {
  asm volatile("{\n.reg .pred p;\nsetp.ne.b32 p, %1, 0;\n@p mbarrier.arrive.shared::cta.b64 _, [%0];\n}" ::"r"(bar), "r"((int)p) : "memory");
}
__device__ __forceinline__ void hint_add_if(bool p, unsigned* a) {
  asm volatile("{\n.reg .pred p;\nsetp.ne.b32 p, %1, 0;\n@p red.relaxed.gpu.global.add.u32 [%0], 1;\n}" ::"l"(a), "r"((int)p) : "memory");
}
__device__ __forceinline__ bool mbar_try(uint32_t bar, uint32_t parity) {
  uint32_t ok;
  asm volatile("{\n.reg .pred p;\nmbarrier.test_wait.parity.shared::cta.b64 p, [%1], %2;\nselp.u32 %0, 1, 0, p;\n}" : "=r"(ok) : "r"(bar), "r"(parity) : "memory");
  return ok;
}
__device__ __forceinline__ void mbar_wait(uint32_t bar, uint32_t parity) {
  asm volatile(
      "{\n.reg .pred p;\n.reg .u32 n;\nmov.u32 n, 0;\n"
      "W_LOOP:\nmbarrier.try_wait.parity.shared::cta.b64 p, [%0], %1;\n@p bra W_DONE;\n"
      "add.u32 n, n, 1;\nsetp.lt.u32 p, n, 0x40000;\n@p bra W_LOOP;\ntrap;\nW_DONE:\n}" ::"r"(bar), "r"(parity) : "memory");
}
__device__ __forceinline__ void bulk_load(uint32_t dst, const void* src, uint32_t bytes, uint32_t bar) {
  asm volatile("cp.async.bulk.shared::cluster.global.mbarrier::complete_tx::bytes [%0], [%1], %2, [%3];" ::"r"(dst), "l"(src), "r"(bytes), "r"(bar) : "memory");
}
__device__ __forceinline__ void spin_guard(uint32_t t0) { if ((uint32_t)clock() - t0 > (1u << 30)) __trap(); }
__device__ __forceinline__ float2 ld_x2(const float2* p) { float2 v; asm volatile("ld.relaxed.gpu.global.v2.f32 {%0,%1}, [%2];" : "=f"(v.x), "=f"(v.y) : "l"(p) : "memory"); return v; }
__device__ __forceinline__ void st_u2(uint2* p, uint32_t a, uint32_t b) { asm volatile("st.relaxed.gpu.global.v2.u32 [%0], {%1,%2};" ::"l"(p), "r"(a), "r"(b) : "memory"); }
__device__ __forceinline__ uint32_t ld_x1(const void* p) { uint32_t v; asm volatile("ld.relaxed.gpu.global.u32 %0, [%1];" : "=r"(v) : "l"(p) : "memory"); return v; }
__device__ __forceinline__ uint4 ld_x4(const void* p) { uint4 v; asm volatile("ld.relaxed.gpu.global.v4.u32 {%0,%1,%2,%3}, [%4];" : "=r"(v.x), "=r"(v.y), "=r"(v.z), "=r"(v.w) : "l"(p) : "memory"); return v; }
__device__ __forceinline__ uint32_t mapa(uint32_t a, uint32_t cta) { uint32_t r; asm volatile("mapa.shared::cluster.u32 %0, %1, %2;" : "=r"(r) : "r"(a), "r"(cta)); return r; }
__device__ __forceinline__ void stsm4t(uint32_t a, uint32_t r0, uint32_t r1, uint32_t r2, uint32_t r3) {
  asm volatile("stmatrix.sync.aligned.m8n8.x4.trans.shared.b16 [%0], {%1,%2,%3,%4};" ::"r"(a), "r"(r0), "r"(r1), "r"(r2), "r"(r3) : "memory");
}
__device__ __forceinline__ void hint_add(unsigned* p) { asm volatile("red.relaxed.gpu.global.add.u32 [%0], 1;" ::"l"(p) : "memory"); }
__device__ __forceinline__ void hint_wait(const unsigned* p, unsigned target) {
  const uint32_t t0 = (uint32_t)clock();
  while ((int)(ld_x1(p) - target) < 0) spin_guard(t0);
}
__device__ __forceinline__ void bulk_done_signal(unsigned* p) {
  asm volatile("cp.async.bulk.commit_group;\ncp.async.bulk.wait_group 0;\nfence.proxy.async.global;" ::: "memory");
  hint_add(p);
}
__device__ __forceinline__ void flag_wait(const unsigned* p, unsigned target) {
  hint_wait(p, target);
  asm volatile("fence.proxy.async.global;" ::: "memory");
}
__device__ __forceinline__ void tma2d(uint32_t dst, const CUtensorMap* m, uint32_t bar, int c0, int c1) {
  asm volatile("cp.async.bulk.tensor.2d.shared::cluster.global.mbarrier::complete_tx::bytes [%0], [%1, {%3, %4}], [%2];" ::"r"(dst), "l"(m), "r"(bar), "r"(c0), "r"(c1) : "memory");
}
__device__ __forceinline__ void tma3d(uint32_t dst, const CUtensorMap* m, uint32_t bar, int c0, int c1, int c2) {
  asm volatile("cp.async.bulk.tensor.3d.shared::cluster.global.mbarrier::complete_tx::bytes [%0], [%1, {%3, %4, %5}], [%2];" ::"r"(dst), "l"(m), "r"(bar), "r"(c0), "r"(c1), "r"(c2) : "memory");
}
__device__ __forceinline__ void tma4d(uint32_t dst, const CUtensorMap* m, uint32_t bar, int c0, int c1, int c2, int c3) {
  asm volatile("cp.async.bulk.tensor.4d.shared::cluster.global.mbarrier::complete_tx::bytes [%0], [%1, {%3, %4, %5, %6}], [%2];" ::"r"(dst), "l"(m), "r"(bar), "r"(c0), "r"(c1), "r"(c2), "r"(c3) : "memory");
}
__device__ __forceinline__ void wg_fence() { asm volatile("wgmma.fence.sync.aligned;" ::: "memory"); }
__device__ __forceinline__ void wg_commit() { asm volatile("wgmma.commit_group.sync.aligned;" ::: "memory"); }
template <int N> __device__ __forceinline__ void wg_wait() { asm volatile("wgmma.wait_group.sync.aligned %0;" ::"n"(N) : "memory"); }
template <int O, int N, int NN> __device__ __forceinline__ void fence_regs(float (&d)[NN]) {
#pragma unroll
  for (int i = 0; i < N; i++) asm volatile("" : "+f"(d[O + i])::"memory");
}
__device__ __forceinline__ uint32_t pack_bf16(float lo, float hi) {
  uint32_t r; asm("cvt.rn.bf16x2.f32 %0, %1, %2;" : "=r"(r) : "f"(hi), "f"(lo)); return r;
}
__device__ __forceinline__ uint32_t pack_pin(float lo, float hi) {
  uint32_t r; asm volatile("cvt.rn.bf16x2.f32 %0, %1, %2;" : "=r"(r) : "f"(hi), "f"(lo) : "memory"); return r;
}
__device__ __forceinline__ uint32_t add_bf2(uint32_t a, uint32_t b) { uint32_t r; asm("add.rn.bf16x2 %0, %1, %2;" : "=r"(r) : "r"(a), "r"(b)); return r; }
__device__ __forceinline__ float bf_lo(uint32_t u) { return __uint_as_float(u << 16); }
__device__ __forceinline__ float bf_hi(uint32_t u) { return __uint_as_float(u & 0xffff0000u); }

__device__ __forceinline__ uint64_t d128(uint32_t lo) { uint64_t d; asm("mov.b64 %0, {%1, 0x40000040};" : "=l"(d) : "r"(lo)); return d; }
__device__ __forceinline__ uint64_t d64(uint32_t lo) { uint64_t d; asm("mov.b64 %0, {%1, 0x80000020};" : "=l"(d) : "r"(lo)); return d; }
template<int O,int TB,int ACC,int NN> __device__ __forceinline__ void mma_ss64(float (&d)[NN], uint64_t da, uint64_t db, int sd = 0){
  if constexpr (ACC == 1) asm volatile("wgmma.mma_async.sync.aligned.m64n64k16.f32.bf16.bf16 {%0,%1,%2,%3,%4,%5,%6,%7,%8,%9,%10,%11,%12,%13,%14,%15,%16,%17,%18,%19,%20,%21,%22,%23,%24,%25,%26,%27,%28,%29,%30,%31}, %32, %33, 1, 1, 1, %35, %34;"
   : "+f"(d[O+0]), "+f"(d[O+1]), "+f"(d[O+2]), "+f"(d[O+3]), "+f"(d[O+4]), "+f"(d[O+5]), "+f"(d[O+6]), "+f"(d[O+7]), "+f"(d[O+8]), "+f"(d[O+9]), "+f"(d[O+10]), "+f"(d[O+11]), "+f"(d[O+12]), "+f"(d[O+13]), "+f"(d[O+14]), "+f"(d[O+15]), "+f"(d[O+16]), "+f"(d[O+17]), "+f"(d[O+18]), "+f"(d[O+19]), "+f"(d[O+20]), "+f"(d[O+21]), "+f"(d[O+22]), "+f"(d[O+23]), "+f"(d[O+24]), "+f"(d[O+25]), "+f"(d[O+26]), "+f"(d[O+27]), "+f"(d[O+28]), "+f"(d[O+29]), "+f"(d[O+30]), "+f"(d[O+31])
   : "l"(da), "l"(db), "n"(TB & 1), "n"(TB >> 1));
  else if constexpr (ACC == 0) asm volatile("wgmma.mma_async.sync.aligned.m64n64k16.f32.bf16.bf16 {%0,%1,%2,%3,%4,%5,%6,%7,%8,%9,%10,%11,%12,%13,%14,%15,%16,%17,%18,%19,%20,%21,%22,%23,%24,%25,%26,%27,%28,%29,%30,%31}, %32, %33, 0, 1, 1, %35, %34;"
   : "=f"(d[O+0]), "=f"(d[O+1]), "=f"(d[O+2]), "=f"(d[O+3]), "=f"(d[O+4]), "=f"(d[O+5]), "=f"(d[O+6]), "=f"(d[O+7]), "=f"(d[O+8]), "=f"(d[O+9]), "=f"(d[O+10]), "=f"(d[O+11]), "=f"(d[O+12]), "=f"(d[O+13]), "=f"(d[O+14]), "=f"(d[O+15]), "=f"(d[O+16]), "=f"(d[O+17]), "=f"(d[O+18]), "=f"(d[O+19]), "=f"(d[O+20]), "=f"(d[O+21]), "=f"(d[O+22]), "=f"(d[O+23]), "=f"(d[O+24]), "=f"(d[O+25]), "=f"(d[O+26]), "=f"(d[O+27]), "=f"(d[O+28]), "=f"(d[O+29]), "=f"(d[O+30]), "=f"(d[O+31])
   : "l"(da), "l"(db), "n"(TB & 1), "n"(TB >> 1));
  else asm volatile("{\n.reg .pred p;\nsetp.ne.b32 p, %36, 0;\nwgmma.mma_async.sync.aligned.m64n64k16.f32.bf16.bf16 {%0,%1,%2,%3,%4,%5,%6,%7,%8,%9,%10,%11,%12,%13,%14,%15,%16,%17,%18,%19,%20,%21,%22,%23,%24,%25,%26,%27,%28,%29,%30,%31}, %32, %33, p, 1, 1, %35, %34;\n}"
   : "+f"(d[O+0]), "+f"(d[O+1]), "+f"(d[O+2]), "+f"(d[O+3]), "+f"(d[O+4]), "+f"(d[O+5]), "+f"(d[O+6]), "+f"(d[O+7]), "+f"(d[O+8]), "+f"(d[O+9]), "+f"(d[O+10]), "+f"(d[O+11]), "+f"(d[O+12]), "+f"(d[O+13]), "+f"(d[O+14]), "+f"(d[O+15]), "+f"(d[O+16]), "+f"(d[O+17]), "+f"(d[O+18]), "+f"(d[O+19]), "+f"(d[O+20]), "+f"(d[O+21]), "+f"(d[O+22]), "+f"(d[O+23]), "+f"(d[O+24]), "+f"(d[O+25]), "+f"(d[O+26]), "+f"(d[O+27]), "+f"(d[O+28]), "+f"(d[O+29]), "+f"(d[O+30]), "+f"(d[O+31])
   : "l"(da), "l"(db), "n"(TB & 1), "n"(TB >> 1), "r"(sd));
}
template<int O,int TB,int ACC,int NN> __device__ __forceinline__ void mma_rs64(float (&d)[NN], uint32_t a0, uint32_t a1, uint32_t a2, uint32_t a3, uint64_t db, int sd = 0){
  if constexpr (ACC == 1) asm volatile("wgmma.mma_async.sync.aligned.m64n64k16.f32.bf16.bf16 {%0,%1,%2,%3,%4,%5,%6,%7,%8,%9,%10,%11,%12,%13,%14,%15,%16,%17,%18,%19,%20,%21,%22,%23,%24,%25,%26,%27,%28,%29,%30,%31}, {%32,%33,%34,%35}, %36, 1, 1, 1, %37;"
   : "+f"(d[O+0]), "+f"(d[O+1]), "+f"(d[O+2]), "+f"(d[O+3]), "+f"(d[O+4]), "+f"(d[O+5]), "+f"(d[O+6]), "+f"(d[O+7]), "+f"(d[O+8]), "+f"(d[O+9]), "+f"(d[O+10]), "+f"(d[O+11]), "+f"(d[O+12]), "+f"(d[O+13]), "+f"(d[O+14]), "+f"(d[O+15]), "+f"(d[O+16]), "+f"(d[O+17]), "+f"(d[O+18]), "+f"(d[O+19]), "+f"(d[O+20]), "+f"(d[O+21]), "+f"(d[O+22]), "+f"(d[O+23]), "+f"(d[O+24]), "+f"(d[O+25]), "+f"(d[O+26]), "+f"(d[O+27]), "+f"(d[O+28]), "+f"(d[O+29]), "+f"(d[O+30]), "+f"(d[O+31])
   : "r"(a0), "r"(a1), "r"(a2), "r"(a3), "l"(db), "n"(TB));
  else if constexpr (ACC == 0) asm volatile("wgmma.mma_async.sync.aligned.m64n64k16.f32.bf16.bf16 {%0,%1,%2,%3,%4,%5,%6,%7,%8,%9,%10,%11,%12,%13,%14,%15,%16,%17,%18,%19,%20,%21,%22,%23,%24,%25,%26,%27,%28,%29,%30,%31}, {%32,%33,%34,%35}, %36, 0, 1, 1, %37;"
   : "=f"(d[O+0]), "=f"(d[O+1]), "=f"(d[O+2]), "=f"(d[O+3]), "=f"(d[O+4]), "=f"(d[O+5]), "=f"(d[O+6]), "=f"(d[O+7]), "=f"(d[O+8]), "=f"(d[O+9]), "=f"(d[O+10]), "=f"(d[O+11]), "=f"(d[O+12]), "=f"(d[O+13]), "=f"(d[O+14]), "=f"(d[O+15]), "=f"(d[O+16]), "=f"(d[O+17]), "=f"(d[O+18]), "=f"(d[O+19]), "=f"(d[O+20]), "=f"(d[O+21]), "=f"(d[O+22]), "=f"(d[O+23]), "=f"(d[O+24]), "=f"(d[O+25]), "=f"(d[O+26]), "=f"(d[O+27]), "=f"(d[O+28]), "=f"(d[O+29]), "=f"(d[O+30]), "=f"(d[O+31])
   : "r"(a0), "r"(a1), "r"(a2), "r"(a3), "l"(db), "n"(TB));
  else asm volatile("{\n.reg .pred p;\nsetp.ne.b32 p, %38, 0;\nwgmma.mma_async.sync.aligned.m64n64k16.f32.bf16.bf16 {%0,%1,%2,%3,%4,%5,%6,%7,%8,%9,%10,%11,%12,%13,%14,%15,%16,%17,%18,%19,%20,%21,%22,%23,%24,%25,%26,%27,%28,%29,%30,%31}, {%32,%33,%34,%35}, %36, p, 1, 1, %37;\n}"
   : "+f"(d[O+0]), "+f"(d[O+1]), "+f"(d[O+2]), "+f"(d[O+3]), "+f"(d[O+4]), "+f"(d[O+5]), "+f"(d[O+6]), "+f"(d[O+7]), "+f"(d[O+8]), "+f"(d[O+9]), "+f"(d[O+10]), "+f"(d[O+11]), "+f"(d[O+12]), "+f"(d[O+13]), "+f"(d[O+14]), "+f"(d[O+15]), "+f"(d[O+16]), "+f"(d[O+17]), "+f"(d[O+18]), "+f"(d[O+19]), "+f"(d[O+20]), "+f"(d[O+21]), "+f"(d[O+22]), "+f"(d[O+23]), "+f"(d[O+24]), "+f"(d[O+25]), "+f"(d[O+26]), "+f"(d[O+27]), "+f"(d[O+28]), "+f"(d[O+29]), "+f"(d[O+30]), "+f"(d[O+31])
   : "r"(a0), "r"(a1), "r"(a2), "r"(a3), "l"(db), "n"(TB), "r"(sd));
}
template<int O,int TB,int ACC,int NN> __device__ __forceinline__ void mma_ss128(float (&d)[NN], uint64_t da, uint64_t db, int sd = 0){
  if constexpr (ACC == 1) asm volatile("wgmma.mma_async.sync.aligned.m64n128k16.f32.bf16.bf16 {%0,%1,%2,%3,%4,%5,%6,%7,%8,%9,%10,%11,%12,%13,%14,%15,%16,%17,%18,%19,%20,%21,%22,%23,%24,%25,%26,%27,%28,%29,%30,%31,%32,%33,%34,%35,%36,%37,%38,%39,%40,%41,%42,%43,%44,%45,%46,%47,%48,%49,%50,%51,%52,%53,%54,%55,%56,%57,%58,%59,%60,%61,%62,%63}, %64, %65, 1, 1, 1, %67, %66;"
   : "+f"(d[O+0]), "+f"(d[O+1]), "+f"(d[O+2]), "+f"(d[O+3]), "+f"(d[O+4]), "+f"(d[O+5]), "+f"(d[O+6]), "+f"(d[O+7]), "+f"(d[O+8]), "+f"(d[O+9]), "+f"(d[O+10]), "+f"(d[O+11]), "+f"(d[O+12]), "+f"(d[O+13]), "+f"(d[O+14]), "+f"(d[O+15]), "+f"(d[O+16]), "+f"(d[O+17]), "+f"(d[O+18]), "+f"(d[O+19]), "+f"(d[O+20]), "+f"(d[O+21]), "+f"(d[O+22]), "+f"(d[O+23]), "+f"(d[O+24]), "+f"(d[O+25]), "+f"(d[O+26]), "+f"(d[O+27]), "+f"(d[O+28]), "+f"(d[O+29]), "+f"(d[O+30]), "+f"(d[O+31]), "+f"(d[O+32]), "+f"(d[O+33]), "+f"(d[O+34]), "+f"(d[O+35]), "+f"(d[O+36]), "+f"(d[O+37]), "+f"(d[O+38]), "+f"(d[O+39]), "+f"(d[O+40]), "+f"(d[O+41]), "+f"(d[O+42]), "+f"(d[O+43]), "+f"(d[O+44]), "+f"(d[O+45]), "+f"(d[O+46]), "+f"(d[O+47]), "+f"(d[O+48]), "+f"(d[O+49]), "+f"(d[O+50]), "+f"(d[O+51]), "+f"(d[O+52]), "+f"(d[O+53]), "+f"(d[O+54]), "+f"(d[O+55]), "+f"(d[O+56]), "+f"(d[O+57]), "+f"(d[O+58]), "+f"(d[O+59]), "+f"(d[O+60]), "+f"(d[O+61]), "+f"(d[O+62]), "+f"(d[O+63])
   : "l"(da), "l"(db), "n"(TB & 1), "n"(TB >> 1));
  else if constexpr (ACC == 0) asm volatile("wgmma.mma_async.sync.aligned.m64n128k16.f32.bf16.bf16 {%0,%1,%2,%3,%4,%5,%6,%7,%8,%9,%10,%11,%12,%13,%14,%15,%16,%17,%18,%19,%20,%21,%22,%23,%24,%25,%26,%27,%28,%29,%30,%31,%32,%33,%34,%35,%36,%37,%38,%39,%40,%41,%42,%43,%44,%45,%46,%47,%48,%49,%50,%51,%52,%53,%54,%55,%56,%57,%58,%59,%60,%61,%62,%63}, %64, %65, 0, 1, 1, %67, %66;"
   : "=f"(d[O+0]), "=f"(d[O+1]), "=f"(d[O+2]), "=f"(d[O+3]), "=f"(d[O+4]), "=f"(d[O+5]), "=f"(d[O+6]), "=f"(d[O+7]), "=f"(d[O+8]), "=f"(d[O+9]), "=f"(d[O+10]), "=f"(d[O+11]), "=f"(d[O+12]), "=f"(d[O+13]), "=f"(d[O+14]), "=f"(d[O+15]), "=f"(d[O+16]), "=f"(d[O+17]), "=f"(d[O+18]), "=f"(d[O+19]), "=f"(d[O+20]), "=f"(d[O+21]), "=f"(d[O+22]), "=f"(d[O+23]), "=f"(d[O+24]), "=f"(d[O+25]), "=f"(d[O+26]), "=f"(d[O+27]), "=f"(d[O+28]), "=f"(d[O+29]), "=f"(d[O+30]), "=f"(d[O+31]), "=f"(d[O+32]), "=f"(d[O+33]), "=f"(d[O+34]), "=f"(d[O+35]), "=f"(d[O+36]), "=f"(d[O+37]), "=f"(d[O+38]), "=f"(d[O+39]), "=f"(d[O+40]), "=f"(d[O+41]), "=f"(d[O+42]), "=f"(d[O+43]), "=f"(d[O+44]), "=f"(d[O+45]), "=f"(d[O+46]), "=f"(d[O+47]), "=f"(d[O+48]), "=f"(d[O+49]), "=f"(d[O+50]), "=f"(d[O+51]), "=f"(d[O+52]), "=f"(d[O+53]), "=f"(d[O+54]), "=f"(d[O+55]), "=f"(d[O+56]), "=f"(d[O+57]), "=f"(d[O+58]), "=f"(d[O+59]), "=f"(d[O+60]), "=f"(d[O+61]), "=f"(d[O+62]), "=f"(d[O+63])
   : "l"(da), "l"(db), "n"(TB & 1), "n"(TB >> 1));
  else asm volatile("{\n.reg .pred p;\nsetp.ne.b32 p, %68, 0;\nwgmma.mma_async.sync.aligned.m64n128k16.f32.bf16.bf16 {%0,%1,%2,%3,%4,%5,%6,%7,%8,%9,%10,%11,%12,%13,%14,%15,%16,%17,%18,%19,%20,%21,%22,%23,%24,%25,%26,%27,%28,%29,%30,%31,%32,%33,%34,%35,%36,%37,%38,%39,%40,%41,%42,%43,%44,%45,%46,%47,%48,%49,%50,%51,%52,%53,%54,%55,%56,%57,%58,%59,%60,%61,%62,%63}, %64, %65, p, 1, 1, %67, %66;\n}"
   : "+f"(d[O+0]), "+f"(d[O+1]), "+f"(d[O+2]), "+f"(d[O+3]), "+f"(d[O+4]), "+f"(d[O+5]), "+f"(d[O+6]), "+f"(d[O+7]), "+f"(d[O+8]), "+f"(d[O+9]), "+f"(d[O+10]), "+f"(d[O+11]), "+f"(d[O+12]), "+f"(d[O+13]), "+f"(d[O+14]), "+f"(d[O+15]), "+f"(d[O+16]), "+f"(d[O+17]), "+f"(d[O+18]), "+f"(d[O+19]), "+f"(d[O+20]), "+f"(d[O+21]), "+f"(d[O+22]), "+f"(d[O+23]), "+f"(d[O+24]), "+f"(d[O+25]), "+f"(d[O+26]), "+f"(d[O+27]), "+f"(d[O+28]), "+f"(d[O+29]), "+f"(d[O+30]), "+f"(d[O+31]), "+f"(d[O+32]), "+f"(d[O+33]), "+f"(d[O+34]), "+f"(d[O+35]), "+f"(d[O+36]), "+f"(d[O+37]), "+f"(d[O+38]), "+f"(d[O+39]), "+f"(d[O+40]), "+f"(d[O+41]), "+f"(d[O+42]), "+f"(d[O+43]), "+f"(d[O+44]), "+f"(d[O+45]), "+f"(d[O+46]), "+f"(d[O+47]), "+f"(d[O+48]), "+f"(d[O+49]), "+f"(d[O+50]), "+f"(d[O+51]), "+f"(d[O+52]), "+f"(d[O+53]), "+f"(d[O+54]), "+f"(d[O+55]), "+f"(d[O+56]), "+f"(d[O+57]), "+f"(d[O+58]), "+f"(d[O+59]), "+f"(d[O+60]), "+f"(d[O+61]), "+f"(d[O+62]), "+f"(d[O+63])
   : "l"(da), "l"(db), "n"(TB & 1), "n"(TB >> 1), "r"(sd));
}
template<int O,int TB,int ACC,int NN> __device__ __forceinline__ void mma_rs128(float (&d)[NN], uint32_t a0, uint32_t a1, uint32_t a2, uint32_t a3, uint64_t db, int sd = 0){
  if constexpr (ACC == 1) asm volatile("wgmma.mma_async.sync.aligned.m64n128k16.f32.bf16.bf16 {%0,%1,%2,%3,%4,%5,%6,%7,%8,%9,%10,%11,%12,%13,%14,%15,%16,%17,%18,%19,%20,%21,%22,%23,%24,%25,%26,%27,%28,%29,%30,%31,%32,%33,%34,%35,%36,%37,%38,%39,%40,%41,%42,%43,%44,%45,%46,%47,%48,%49,%50,%51,%52,%53,%54,%55,%56,%57,%58,%59,%60,%61,%62,%63}, {%64,%65,%66,%67}, %68, 1, 1, 1, %69;"
   : "+f"(d[O+0]), "+f"(d[O+1]), "+f"(d[O+2]), "+f"(d[O+3]), "+f"(d[O+4]), "+f"(d[O+5]), "+f"(d[O+6]), "+f"(d[O+7]), "+f"(d[O+8]), "+f"(d[O+9]), "+f"(d[O+10]), "+f"(d[O+11]), "+f"(d[O+12]), "+f"(d[O+13]), "+f"(d[O+14]), "+f"(d[O+15]), "+f"(d[O+16]), "+f"(d[O+17]), "+f"(d[O+18]), "+f"(d[O+19]), "+f"(d[O+20]), "+f"(d[O+21]), "+f"(d[O+22]), "+f"(d[O+23]), "+f"(d[O+24]), "+f"(d[O+25]), "+f"(d[O+26]), "+f"(d[O+27]), "+f"(d[O+28]), "+f"(d[O+29]), "+f"(d[O+30]), "+f"(d[O+31]), "+f"(d[O+32]), "+f"(d[O+33]), "+f"(d[O+34]), "+f"(d[O+35]), "+f"(d[O+36]), "+f"(d[O+37]), "+f"(d[O+38]), "+f"(d[O+39]), "+f"(d[O+40]), "+f"(d[O+41]), "+f"(d[O+42]), "+f"(d[O+43]), "+f"(d[O+44]), "+f"(d[O+45]), "+f"(d[O+46]), "+f"(d[O+47]), "+f"(d[O+48]), "+f"(d[O+49]), "+f"(d[O+50]), "+f"(d[O+51]), "+f"(d[O+52]), "+f"(d[O+53]), "+f"(d[O+54]), "+f"(d[O+55]), "+f"(d[O+56]), "+f"(d[O+57]), "+f"(d[O+58]), "+f"(d[O+59]), "+f"(d[O+60]), "+f"(d[O+61]), "+f"(d[O+62]), "+f"(d[O+63])
   : "r"(a0), "r"(a1), "r"(a2), "r"(a3), "l"(db), "n"(TB));
  else if constexpr (ACC == 0) asm volatile("wgmma.mma_async.sync.aligned.m64n128k16.f32.bf16.bf16 {%0,%1,%2,%3,%4,%5,%6,%7,%8,%9,%10,%11,%12,%13,%14,%15,%16,%17,%18,%19,%20,%21,%22,%23,%24,%25,%26,%27,%28,%29,%30,%31,%32,%33,%34,%35,%36,%37,%38,%39,%40,%41,%42,%43,%44,%45,%46,%47,%48,%49,%50,%51,%52,%53,%54,%55,%56,%57,%58,%59,%60,%61,%62,%63}, {%64,%65,%66,%67}, %68, 0, 1, 1, %69;"
   : "=f"(d[O+0]), "=f"(d[O+1]), "=f"(d[O+2]), "=f"(d[O+3]), "=f"(d[O+4]), "=f"(d[O+5]), "=f"(d[O+6]), "=f"(d[O+7]), "=f"(d[O+8]), "=f"(d[O+9]), "=f"(d[O+10]), "=f"(d[O+11]), "=f"(d[O+12]), "=f"(d[O+13]), "=f"(d[O+14]), "=f"(d[O+15]), "=f"(d[O+16]), "=f"(d[O+17]), "=f"(d[O+18]), "=f"(d[O+19]), "=f"(d[O+20]), "=f"(d[O+21]), "=f"(d[O+22]), "=f"(d[O+23]), "=f"(d[O+24]), "=f"(d[O+25]), "=f"(d[O+26]), "=f"(d[O+27]), "=f"(d[O+28]), "=f"(d[O+29]), "=f"(d[O+30]), "=f"(d[O+31]), "=f"(d[O+32]), "=f"(d[O+33]), "=f"(d[O+34]), "=f"(d[O+35]), "=f"(d[O+36]), "=f"(d[O+37]), "=f"(d[O+38]), "=f"(d[O+39]), "=f"(d[O+40]), "=f"(d[O+41]), "=f"(d[O+42]), "=f"(d[O+43]), "=f"(d[O+44]), "=f"(d[O+45]), "=f"(d[O+46]), "=f"(d[O+47]), "=f"(d[O+48]), "=f"(d[O+49]), "=f"(d[O+50]), "=f"(d[O+51]), "=f"(d[O+52]), "=f"(d[O+53]), "=f"(d[O+54]), "=f"(d[O+55]), "=f"(d[O+56]), "=f"(d[O+57]), "=f"(d[O+58]), "=f"(d[O+59]), "=f"(d[O+60]), "=f"(d[O+61]), "=f"(d[O+62]), "=f"(d[O+63])
   : "r"(a0), "r"(a1), "r"(a2), "r"(a3), "l"(db), "n"(TB));
  else asm volatile("{\n.reg .pred p;\nsetp.ne.b32 p, %70, 0;\nwgmma.mma_async.sync.aligned.m64n128k16.f32.bf16.bf16 {%0,%1,%2,%3,%4,%5,%6,%7,%8,%9,%10,%11,%12,%13,%14,%15,%16,%17,%18,%19,%20,%21,%22,%23,%24,%25,%26,%27,%28,%29,%30,%31,%32,%33,%34,%35,%36,%37,%38,%39,%40,%41,%42,%43,%44,%45,%46,%47,%48,%49,%50,%51,%52,%53,%54,%55,%56,%57,%58,%59,%60,%61,%62,%63}, {%64,%65,%66,%67}, %68, p, 1, 1, %69;\n}"
   : "+f"(d[O+0]), "+f"(d[O+1]), "+f"(d[O+2]), "+f"(d[O+3]), "+f"(d[O+4]), "+f"(d[O+5]), "+f"(d[O+6]), "+f"(d[O+7]), "+f"(d[O+8]), "+f"(d[O+9]), "+f"(d[O+10]), "+f"(d[O+11]), "+f"(d[O+12]), "+f"(d[O+13]), "+f"(d[O+14]), "+f"(d[O+15]), "+f"(d[O+16]), "+f"(d[O+17]), "+f"(d[O+18]), "+f"(d[O+19]), "+f"(d[O+20]), "+f"(d[O+21]), "+f"(d[O+22]), "+f"(d[O+23]), "+f"(d[O+24]), "+f"(d[O+25]), "+f"(d[O+26]), "+f"(d[O+27]), "+f"(d[O+28]), "+f"(d[O+29]), "+f"(d[O+30]), "+f"(d[O+31]), "+f"(d[O+32]), "+f"(d[O+33]), "+f"(d[O+34]), "+f"(d[O+35]), "+f"(d[O+36]), "+f"(d[O+37]), "+f"(d[O+38]), "+f"(d[O+39]), "+f"(d[O+40]), "+f"(d[O+41]), "+f"(d[O+42]), "+f"(d[O+43]), "+f"(d[O+44]), "+f"(d[O+45]), "+f"(d[O+46]), "+f"(d[O+47]), "+f"(d[O+48]), "+f"(d[O+49]), "+f"(d[O+50]), "+f"(d[O+51]), "+f"(d[O+52]), "+f"(d[O+53]), "+f"(d[O+54]), "+f"(d[O+55]), "+f"(d[O+56]), "+f"(d[O+57]), "+f"(d[O+58]), "+f"(d[O+59]), "+f"(d[O+60]), "+f"(d[O+61]), "+f"(d[O+62]), "+f"(d[O+63])
   : "r"(a0), "r"(a1), "r"(a2), "r"(a3), "l"(db), "n"(TB), "r"(sd));
}

#define NEARLY 0
#define XAHEAD 3
#define HEADN 6
#define WBATCH 1
#define WB 8
#define WSLEEP 20
#define XSPREAD 4
#define NOSEND 0
#define MSPLIT 3
#define PFALL 1
#define L2PF 1
#define STAG 0
#define EPF 2
#define XNB 2
#define FNB 0
#define GNB 0
#define TH 5
#define PF0 4
#define FSPLIT 1
#define MGLU 1
#define SPC 2
#define TL 14
#define SPACE 40
#define WPF 1
#define WAFTER 7
#define WPACE 0
#define GATE_AT 4
#define TPACE 40
#define PFMODE 0
#define MAPMODE 1
template <int V> struct IC { static constexpr int value = V; };
struct Maps { CUtensorMap x, ft, g64, u64, e, wr, wi, xs, ts, t, g32, u32, d224, o; };

constexpr int NCTA = 130;
constexpr int U = 16384;
constexpr int TB = 36864;
constexpr int OFF_RING = 8 * U, OFF_Z = 12 * U, OFF_XB = 12 * U, OFF_T = 13 * U, OFF_D = OFF_T;
constexpr int OFF_BAR = 14 * U, OFF_SP = OFF_BAR + 512, OFF_G = OFF_SP + 1024 + 128;
constexpr int SMEM_BYTES = OFF_G + 512;
constexpr int B_FX = 0, B_FA = 8, B_FT = 12, B_Z = 16, B_W = 24, B_HX = 25, B_TL = 26, B_HP = 27, B_WR = 30, B_E0 = 34;
constexpr int B_EA = 35, B_ET = 39, B_PZ = 43, B_RDY = 45, B_FE = 46;
constexpr int B_T = 50, B_XS = 51, B_G = 53, B_RD0 = 54, NBAR = 55;
__host__ __device__ constexpr int rslot(int n) { return n & 3; }
__host__ __device__ constexpr int rpar(int n) { return (n >> 2) & 1; }

__global__ void __cluster_dims__(2, 1, 1) __launch_bounds__(512, 1)
fused_kernel(Work* __restrict__ ws, const uint16_t* __restrict__ dtab, const __nv_bfloat16* __restrict__ w_r, const __nv_bfloat16* __restrict__ w_i,
             const __nv_bfloat16* __restrict__ gate_w, const __nv_bfloat16* __restrict__ x, const __grid_constant__ Maps maps) {
  extern __shared__ __align__(1024) uint8_t smem[];
  if (threadIdx.x < 32 && elect_one()) {
#pragma unroll
    for (int i = 0; i < PF0; i++) asm volatile("prefetch.tensormap [%0];" ::"l"((const char*)&maps + i * 128) : "memory");
  }
  const uint32_t sb = smem_u32(smem);
  const uint32_t bars = sb + OFF_BAR;
  const int tid = threadIdx.x, lane = tid & 31;
  const int warp = __shfl_sync(0xffffffffu, tid >> 5, 0);
  const bool helper = blockIdx.x >= 128;
  const int cl = (blockIdx.x >> 1) & 63, rank = blockIdx.x & 1;
  const int q4 = (cl & 1) | ((cl >> 2) & 2), rb = ((cl >> 1) & 3) | ((cl >> 4) << 2);
  const int j = 2 * q4 + rank;
  const int f_full = 448 * q4 + (rank ? 256 : 0);
  const int f_half = 448 * q4 + (rank ? 224 : 192);
  const int kg = 2 * j + (rb >> 3), tn = rb & 7;

  if (tid == 64) { PROF_EV(0); PROF_CK(40); }
  if (warp < 8) {
    if (!helper && tid < 32) {
      const int r = 16 * j + (tid & 15);
      asm volatile("prefetch.global.L2 [%0];" ::"l"(x + (size_t)(2 * rb + (r >> 6) + 32 * (r & 63)) * 512 + 64 * (tid >> 4)));
    }
    asm volatile("barrier.cluster.arrive.relaxed.aligned;" ::: "memory");
    asm volatile("setmaxnreg.inc.sync.aligned.u32 192;");
    if (!helper) {
      const int wg = warp >> 2, w = warp & 3, g = lane >> 2;
      const bool elect = (tid & 127) == 0;
      float cX[32], cA[64], cB[64], cC[64], ci[64], ct[64];
      const int zero = blockIdx.x >> 16;
      uint32_t h[56], yf[16];
      const uint32_t d0 = (sb & 0x3FFFF) >> 4;
      const uint32_t dK = d0 | (1u << 16), dN = d0 | (512u << 16);
      const uint32_t dX = dK + wg * 512;
      constexpr uint32_t RING = OFF_RING >> 4;
      auto waitA = [&](int n) { mbar_wait(bars + 8 * (B_FA + rslot(n)), rpar(n)); };
      auto freeA = [&](int n) { mbar_arrive_if(elect, bars + 8 * (B_EA + rslot(n))); };
      auto nop = [] {};

      asm volatile("bar.sync 0, 384;" ::: "memory");
#pragma unroll 1
      for (int i = 0; i < 4; i++) {
        const uint64_t dx = d128(dX + i * 2048), df = d128(dK + (OFF_XB >> 4) + (i & 1) * 1024);
        mbar_wait(bars + 8 * (B_FX + 2 * i), 0);
        wg_fence();
        mma_ss64<0, 0, 2>(cX, df, dx, i);
        mma_ss64<0, 0, 1>(cX, df + 2, dx + 2);
        wg_commit(); wg_wait<1>();
        mbar_arrive_if(elect && i, bars + 8 * (B_EA + rslot(i - 1)));
        mma_ss64<0, 0, 1>(cX, df + 4, dx + 4);
        mma_ss64<0, 0, 1>(cX, df + 6, dx + 6);
        if (i == 0 && tid == 0) PROF_EV(1);
        mbar_wait(bars + 8 * (B_FX + 2 * i + 1), 0);
        wg_fence();
#pragma unroll
        for (int k = 0; k < 4; k++) mma_ss64<0, 0, 1>(cX, df + (512 + k * 2), dx + (1024 + k * 2));
        wg_commit();
        waitA(i);
        wg_fence();
        const uint64_t da = d128(dX + i * 1024), db = d128(dN + RING + i * 1024);
        mma_ss128<0, 1, 2>(cA, da, db, i);
        wg_commit(); wg_wait<1>();
        mbar_arrive_if(elect, bars + 8 * (B_FE + i));
#pragma unroll
        for (int k = 1; k < 4; k++) mma_ss128<0, 1, 1>(cA, da + k * 2, db + k * 128);
        wg_commit();
      }
      fence_regs<0, 32>(cX);
#pragma unroll
      for (int e = 0; e < 16; e++) yf[e] = pack_pin(cX[2 * e], cX[2 * e + 1]);
      if (tid == 0) { PROF_EV(2); PROF_CK(42); }
      {
        waitA(4); mbar_wait(bars + 8 * B_E0, 0);
        const uint64_t de = d128(dN + (wg ? RING : OFF_XB >> 4));
        wg_fence();
        mma_rs128<0, 1, 0>(cB, yf[0], yf[1], yf[2], yf[3], de);
        wg_commit();
        wg_wait<1>();
        freeA(3);
#pragma unroll
        for (int k = 1; k < 4; k++) mma_rs128<0, 1, 1>(cB, yf[4 * k], yf[4 * k + 1], yf[4 * k + 2], yf[4 * k + 3], de + k * 128);
        wg_commit();
      }
      bool rel = false;
      auto acquire = [&](int n) {
        rel = elect;
        if (!mbar_try(bars + 8 * (B_FA + rslot(n)), rpar(n))) { wg_wait<0>(); freeA(n - 1); rel = false; waitA(n); }
      };
      auto freeP = [&](int n) { mbar_arrive_if(rel, bars + 8 * (B_EA + rslot(n - 1))); };
      auto ffn_step = [&](auto first, auto split, float (&acc)[64], int n, int kb, auto done, auto work) {
        constexpr int SPLIT = decltype(split)::value;
        acquire(n);
        wg_fence();
        const uint64_t dx = d128(dX + kb * 1024), db = d128(dN + RING + rslot(n) * 1024);
        mma_ss128<0, 1, decltype(first)::value>(acc, dx, db, kb);
#pragma unroll
        for (int k = 1; k < SPLIT; k++) mma_ss128<0, 1, 1>(acc, dx + k * 2, db + k * 128);
        wg_commit();
        work();
        wg_wait<1>();
        freeP(n);
        done();
        if (SPLIT < 4) {
          wg_fence();
#pragma unroll
          for (int k = SPLIT; k < 4; k++) mma_ss128<0, 1, 1>(acc, dx + k * 2, db + k * 128);
          wg_commit();
        }
      };
      {
        const int s0 = 2 * rb + wg, kr = 2 * ((s0 & 1) | ((s0 & 4) >> 1));
        const int m = lane >> 3, r = lane & 7;
        const uint32_t a0 = sb + OFF_XB + wg * 8192 + (((w >> 1) * 8 + (m >> 1)) * 2 + (w & 1)) * 256 + (m & 1) * 128 + ((r ^ (kr + (m & 1))) << 4);
        ffn_step(IC<1>(), IC<4>(), cA, 5, 4, [&] { fence_regs<0, 64>(cB); }, nop);
        asm volatile("bar.sync 5, 256;" ::: "memory");
        auto stage = [&](int i) {
          stsm4t(a0 + i * 1024, pack_bf16(cB[8 * i] - cB[34 + 8 * i], cB[8 * i + 1] - cB[35 + 8 * i]),
                 pack_bf16(cB[32 + 8 * i] + cB[8 * i + 2], cB[33 + 8 * i] + cB[8 * i + 3]),
                 pack_bf16(cB[8 * i + 4] - cB[38 + 8 * i], cB[8 * i + 5] - cB[39 + 8 * i]),
                 pack_bf16(cB[36 + 8 * i] + cB[8 * i + 6], cB[37 + 8 * i] + cB[8 * i + 7]));
          if (j == 0 && w == 0) {
            const uint32_t a1 = r ? sb + OFF_SP + 1024 : sb + OFF_SP + wg * 512 + (m & 1) * 256 + (m >> 1) * 128;
#pragma unroll
            for (int n = 2 * i; n < 2 * i + 2; n++)
              asm volatile("stmatrix.sync.aligned.m8n8.x4.shared.b16 [%0], {%1,%2,%3,%4};" ::"r"(a1 + ((n ^ (kr + (m >> 1)) ^ r) << 4)),
                           "r"(pack_bf16(cB[4 * n], cB[4 * n + 1])), "r"(pack_bf16(cB[4 * n + 2], cB[4 * n + 3])),
                           "r"(pack_bf16(cB[32 + 4 * n], cB[33 + 4 * n])), "r"(pack_bf16(cB[34 + 4 * n], cB[35 + 4 * n])) : "memory");
          }
        };
        auto publish = [&] {
          asm volatile("fence.proxy.async.shared::cta;" ::: "memory");
          __syncwarp();
          mbar_arrive_if(lane == 0, bars + 8 * (B_XS + wg));
          if (tid == 0) PROF_EV(3);
        };
        stage(0);
        ffn_step(IC<1>(), IC<FSPLIT>(), cA, 6, 5, nop, nop);
        stage(1);
        ffn_step(IC<1>(), IC<FSPLIT>(), cA, 7, 6, nop, nop);
        stage(2);
        ffn_step(IC<1>(), IC<2>(), cA, 8, 7, [&] { stage(3); }, nop);
        publish();
      }
      float g0 = 0.f, g1 = 0.f;
      uint32_t tag = 0;
      uint32_t ob[2] = {0, 0};
      auto glu = [&](auto& acc, int half, int ho, int i0, int i1) {
#pragma unroll
        for (int i = i0; i < i1; i++)
          asm volatile("{\n.reg .b32 a, b;\ncvt.rn.relu.bf16x2.f32 a, %2, %1;\ncvt.rn.bf16x2.f32 b, %4, %3;\nmul.rn.bf16x2 a, a, b;\nmul.rn.bf16x2 %0, a, %5;\n}"
                       : "=r"(h[ho + i]) : "f"(acc[2 * i]), "f"(acc[2 * i + 1]), "f"(acc[half + 2 * i]), "f"(acc[half + 1 + 2 * i]), "r"(ob[i & 1]) : "memory");
      };
      ffn_step(IC<2>(), IC<1>(), cB, 9, zero, nop, nop);
#pragma unroll 1
      for (int kb = 1; kb < 8; kb++)
        ffn_step(IC<1>(), IC<FSPLIT>(), cB, 9 + kb, kb, nop, [&] {
          if (kb == 4 + 2 * wg) {
            mbar_wait(bars + 8 * B_G, 0);
            const uint32_t gb0 = *(const uint32_t*)(smem + OFF_G + (wg * 64 + w * 16 + g) * 4), gb1 = *(const uint32_t*)(smem + OFF_G + (wg * 64 + w * 16 + g + 8) * 4);
            tag = gb0 & 1; g0 = __uint_as_float(gb0 & ~1u); g1 = __uint_as_float(gb1 & ~1u);
            ob[0] = pack_bf16(1.0f - g0, 1.0f - g0); ob[1] = pack_bf16(1.0f - g1, 1.0f - g1);
            glu(cA, 32, 0, 0, 16);
          }
        });
      if (tid == 0) { PROF_EV(4); PROF_CK(43); }
      auto m_step = [&](auto first, int i) {
        acquire(17 + i);
        wg_fence();
        const uint64_t dx = d128(dX + i * 2048), dm = d64(dN + RING + rslot(17 + i) * 1024);
        mma_ss64<0, 1, decltype(first)::value>(ct, dx, dm);
#pragma unroll
        for (int k = 1; k < MSPLIT; k++) mma_ss64<0, 1, 1>(ct, dx + ((k >> 2) * 1024 + (k & 3) * 2), dm + k * 64);
        wg_commit();
        wg_wait<1>();
        freeP(17 + i);
        wg_fence();
#pragma unroll
        for (int k = MSPLIT; k < 8; k++) mma_ss64<0, 1, 1>(ct, dx + ((k >> 2) * 1024 + (k & 3) * 2), dm + k * 64);
        wg_commit();
      };
      m_step(IC<0>(), 0);
#pragma unroll 1
      for (int i = 1; i < 5; i++) {
        if (i == 1 + 2 * wg) glu(cB, 32, 16, 0, 16);
        if (i < 4) m_step(IC<1>(), i);
      }
      if (tid == 0) { PROF_EV(5); PROF_CK(44); }
      ffn_step(IC<0>(), IC<1>(), cC, 21, 0, nop, nop);
#pragma unroll 1
      for (int kb = 1; kb < 8; kb++)
        ffn_step(IC<1>(), IC<FSPLIT>(), cC, 21 + kb, kb, [&] { mbar_arrive_if(elect && !(kb & 1), bars + 8 * (B_ET + (kb >> 1) - 1)); }, [&] {
          if (kb == 1 + wg) glu(ct, 16, 48, 0, 8);
        });

      auto twait = [&](uint32_t bar, uint32_t par, int) { mbar_wait(bar, par); };
      const int fo = warp * 128 + lane;
      auto fetch = [&](uint4 (&pv)[4], int z) {
        twait(bars + 8 * (z < 4 ? B_Z + 2 * z + wg : B_HP + z - 4), 0, 8 + z);
        const uint8_t* src = smem + (z < 4 ? OFF_Z - z * U : z == 4 ? OFF_T : (z - 5) * U) + fo * 16;
#pragma unroll
        for (int i = 0; i < 4; i++) pv[i] = *(const uint4*)(src + i * 512);
      };
      auto check = [&](uint4 (&pv)[4], int z) {
        const uint32_t t0 = (uint32_t)clock();
        while (__any_sync(0xffffffffu, ((pv[0].x ^ tag) | (pv[1].x ^ tag) | (pv[2].x ^ tag) | (pv[3].x ^ tag)) & 1)) {
#pragma unroll
          for (int i = 0; i < 4; i++) pv[i] = ld_x4(ws->part + (size_t)((rb * 8 + j) * 3 + z - 4) * 1024 + fo + i * 32);
          spin_guard(t0);
        }
#pragma unroll
        for (int i = 0; i < 4; i++) pv[i].x &= ~1u;
      };
      const uint32_t peerZ = mapa(sb + OFF_Z + fo * 16, rank ^ 1), peerB = mapa(bars + 8 * (B_Z + wg), rank ^ 1);
      auto tile_mma = [&](auto off, int t, int k0, int k1, int init) {
        constexpr int O = decltype(off)::value;
        const uint64_t db = d128(dN + (t & 3) * (TB >> 4)), dw = db + rank * 256, dm = db + (rank ? 0 : 1536);
#pragma unroll
        for (int k = k0; k < k1; k++) {
          if (k == 0) mma_rs64<O, 1, 2>(ct, h[0], h[1], h[2], h[3], dw, init);
          else if (k < 14) mma_rs64<O, 1, 1>(ct, h[4 * k], h[4 * k + 1], h[4 * k + 2], h[4 * k + 3], k < 12 ? dw + k * 128 : dm + (k - 12) * 128);
          else mma_rs64<O, 1, 1>(ct, yf[4 * k - 56], yf[4 * k - 55], yf[4 * k - 54], yf[4 * k - 53], db + k * 128);
        }
      };
      uint4 pv[4] = {};
      auto tile = [&](auto off, int t) {
        constexpr int P = 32 - decltype(off)::value;
        const bool grid = t >= 4 && t < 7, pre = t >= 3 && t != 6;
        const int zo = grid ? t - 4 : t == 7 ? 3 : t - 1, z = t - 3;
        const int owner = rb * 8 + 2 * ((q4 + zo + 1) & 3) + rank;
        uint4* dst = ws->part + (size_t)(owner * 3 + zo) * 1024 + fo;
        const uint32_t src = sb + (z < 4 ? OFF_Z - z * U : OFF_T) + fo * 16;
        twait(bars + 8 * (B_FT + (t & 3)), t >> 2, t);
        wg_fence();
        tile_mma(off, t, 0, TH, zero);
        wg_commit();
        wg_wait<1>();
        mbar_arrive_if(elect && t < 6, bars + 8 * (B_ET + t - 1));
        if (t < 3) twait(bars + 8 * (t == 1 ? B_RD0 : B_RDY), 0, 14 + t);
        fence_regs<P, 32>(ct);
#pragma unroll
        for (int i = 0; i < 4; i++) {
          pv[i].x = (add_bf2(pv[i].x, pack_bf16(ct[P + 8 * i], ct[P + 8 * i + 1])) & ~(uint32_t)grid) | (tag & grid);
          pv[i].y = add_bf2(pv[i].y, pack_bf16(ct[P + 8 * i + 2], ct[P + 8 * i + 3]));
          pv[i].z = add_bf2(pv[i].z, pack_bf16(ct[P + 8 * i + 4], ct[P + 8 * i + 5]));
          pv[i].w = add_bf2(pv[i].w, pack_bf16(ct[P + 8 * i + 6], ct[P + 8 * i + 7]));
        }
        if (grid) {
#pragma unroll
          for (int i = 0; i < 4; i++)
            asm volatile("st.relaxed.gpu.global.v4.u32 [%0], {%1,%2,%3,%4};" ::"l"(dst + i * 32), "r"(pv[i].x), "r"(pv[i].y), "r"(pv[i].z), "r"(pv[i].w) : "memory");
          hint_add_if(lane == 0, &ws->cntP[32 * owner + zo]);
        }
#pragma unroll
        for (int i = 0; i < 4; i++) {
          if (!grid)
            asm volatile("st.async.weak.shared::cluster.mbarrier::complete_tx::bytes.v4.b32 [%0], {%2,%3,%4,%5}, [%1];" ::"r"(peerZ - zo * U + i * 512),
                         "r"(peerB + 16 * zo), "r"(pv[i].x), "r"(pv[i].y), "r"(pv[i].z), "r"(pv[i].w) : "memory");
          wg_fence();
          tile_mma(off, t, TH + SPC * i, i < 3 ? TH + SPC * i + SPC : TL, 0);
        }
        wg_commit();
        if (pre) twait(bars + 8 * (z < 4 ? B_Z + 2 * z + wg : B_HP), 0, 8 + z);
        wg_fence();
#pragma unroll
        for (int i = 0; i < 4; i++) {
          asm volatile("{\n.reg .pred p;\nsetp.ne.b32 p, %5, 0;\nmov.b32 %0, 0;\nmov.b32 %1, 0;\nmov.b32 %2, 0;\nmov.b32 %3, 0;\n@p ld.shared.v4.u32 {%0,%1,%2,%3}, [%4];\n}"
                       : "=r"(pv[i].x), "=r"(pv[i].y), "=r"(pv[i].z), "=r"(pv[i].w) : "r"(src + i * 512), "r"((int)pre) : "memory");
          tile_mma(off, t, TL + i, i < 3 ? TL + 1 + i : 18, 0);
        }
        wg_commit();
      };
      asm volatile("barrier.cluster.wait.aligned;" ::: "memory");
      twait(bars + 8 * B_FT, 0, 0);
      wg_fence();
      tile_mma(IC<0>(), 0, 0, 5, zero);
      wg_commit();
      wg_wait<1>();
      mbar_arrive_if(elect, bars + 8 * (B_ET + 3));
      glu(cC, 32, 32, 0, 8);
      waitA(29 + wg);
      wg_fence();
      tile_mma(IC<0>(), 0, 5, 8, 0);
      tile_mma(IC<0>(), 0, 12, 14, 0);
      wg_commit();
      glu(cC, 32, 32, 8, 16);
      if (tid == 0) PROF_EV(6);
      if (tid == 128) PROF_EV(27);
      mbar_wait(bars + 8 * (j == 0 ? B_T : B_TL), 0);
      if (tid == 0) { PROF_EV(7); PROF_CK(45); }
      wg_fence();
      {
        const uint64_t dt = d128(dN + (OFF_T >> 4) + wg * 512), de = d128(dK + RING + (1 + wg) * 1024);
        mma_ss64<0, 1, 0>(ci, de, dt);
        mma_ss64<32, 1, 0>(ci, de + 512, dt);
#pragma unroll
        for (int k = 1; k < 4; k++) {
          mma_ss64<0, 1, 1>(ci, de + k * 2, dt + k * 128);
          mma_ss64<32, 1, 1>(ci, de + (512 + k * 2), dt + k * 128);
        }
        wg_commit();
      }
      tile_mma(IC<0>(), 0, 8, 12, 0);
      wg_commit();
      wg_wait<1>();
      if (elect) asm volatile("mbarrier.arrive.shared::cluster.b64 _, [%0];" ::"r"(mapa(bars + 8 * B_RDY, rank ^ 1)) : "memory");
      mbar_arrive_if(elect, bars + 8 * (B_PZ + 1));
      fence_regs<0, 64>(ci);
#pragma unroll
      for (int i = 0; i < 16; i++) {
        const float gg = ((i & 1) ? g1 : g0) * (2.0f / (2048.0f * 512.0f));
        if (i & 2) yf[i] = pack_pin((ci[2 * i] - ci[28 + 2 * i]) * gg, (ci[2 * i + 1] - ci[29 + 2 * i]) * gg);
        else yf[i] = pack_pin((ci[2 * i] + ci[36 + 2 * i]) * gg, (ci[2 * i + 1] + ci[37 + 2 * i]) * gg);
      }
      wg_fence();
      tile_mma(IC<0>(), 0, 14, 18, 0);
      wg_commit();
      if (tid == 0) PROF_EV(8);
      if (tid == 128) PROF_EV(28);
#pragma unroll 1
      for (int t = 1;; t += 2) {
        tile(IC<32>(), t);
        if (t == 7) break;
        tile(IC<0>(), t + 1);
      }
      if (tid == 0) { PROF_EV(9); PROF_CK(46); }
      if (tid == 128) PROF_EV(29);
      {
        uint4 p1[4], p2[4];
        auto acc4 = [&](uint4 (&d)[4], const uint4 (&a)[4]) {
#pragma unroll
          for (int i = 0; i < 4; i++) { d[i].x = add_bf2(d[i].x, a[i].x); d[i].y = add_bf2(d[i].y, a[i].y); d[i].z = add_bf2(d[i].z, a[i].z); d[i].w = add_bf2(d[i].w, a[i].w); }
        };
        fetch(p1, 5);
        check(pv, 4); check(p1, 5);
        acc4(pv, p1);
        fetch(p1, 3);
        if (tid == 0) PROF_EV(25);
        fetch(p2, 6);
        if (tid == 0) PROF_EV(24);
        check(p2, 6);
        acc4(p1, p2); acc4(pv, p1);
        const uint32_t ps[16] = {pv[0].x, pv[0].y, pv[0].z, pv[0].w, pv[1].x, pv[1].y, pv[1].z, pv[1].w, pv[2].x, pv[2].y, pv[2].z, pv[2].w, pv[3].x, pv[3].y, pv[3].z, pv[3].w};
        if (tid == 0) PROF_EV(14);
        wg_wait<0>();
        fence_regs<32, 32>(ct);
        float sum[32];
#pragma unroll
        for (int i = 0; i < 16; i++) { sum[2 * i] = ct[32 + 2 * i] + bf_lo(ps[i]); sum[2 * i + 1] = ct[33 + 2 * i] + bf_hi(ps[i]); }
        const uint32_t stg = sb + OFF_T + warp * 2048;
        const int mr = (lane & 7) + ((lane >> 3) & 1) * 8, mc = lane >> 4;
#pragma unroll
        for (int i = 0; i < 4; i++) {
          const uint32_t a = stg + mr * 128 + (((2 * i + mc) ^ (mr & 7)) << 4);
          asm volatile("stmatrix.sync.aligned.m8n8.x4.shared.b16 [%0], {%1,%2,%3,%4};" ::"r"(a), "r"(pack_bf16(sum[8 * i], sum[8 * i + 1])),
                       "r"(pack_bf16(sum[8 * i + 2], sum[8 * i + 3])), "r"(pack_bf16(sum[8 * i + 4], sum[8 * i + 5])),
                       "r"(pack_bf16(sum[8 * i + 6], sum[8 * i + 7])) : "memory");
        }
        asm volatile("fence.proxy.async.shared::cta;" ::: "memory");
        __syncwarp();
        if (elect_one()) {
          asm volatile("cp.async.bulk.tensor.3d.global.shared::cta.bulk_group [%0, {%2, %3, %4}], [%1];" ::"l"(&maps.o), "r"(stg), "r"(64 * j),
                       "r"(16 * w), "r"(2 * rb + wg) : "memory");
          asm volatile("cp.async.bulk.commit_group;\ncp.async.bulk.wait_group.read 0;" ::: "memory");
        }
      }
      if (tid == 0) { PROF_EV(15); PROF_CK(41); }
      if (tid == 128) PROF_EV(30);
    }
  } else if (warp < 12) {
    asm volatile("setmaxnreg.dec.sync.aligned.u32 104;");
    asm volatile("barrier.cluster.arrive.relaxed.aligned;" ::: "memory");
    const int t = tid - 256, w = warp - 8;
    const uint32_t ep = ld_x1(&ws->epoch[blockIdx.x * 8]);
    const uint32_t tag = (ep + 1) & 1;
    auto w_issue = [&](const CUtensorMap* m) {

      if (elect_one()) { mbar_expect_tx(bars + 8 * (B_WR + w), 3072); tma4d(sb + OFF_T + w * 3072, m, bars + 8 * (B_WR + w), 16 * kg, 0, 2 * w, tn); }

          __syncwarp();
    };
    auto gate_rows = [&] {
      const int r = 16 * j + 4 * w + (lane >> 3);
      const uint4* pg = (const uint4*)gate_w + (lane & 7);
      {
        float a = 0.f;
        asm volatile("bar.sync 4, 256;" ::: "memory");
#pragma unroll 1
        for (int hf = 0; hf < 2; hf++) {
          uint4 v[4], u[4];
#pragma unroll
          for (int kb = 0; kb < 4; kb++) v[kb] = __ldg(pg + (4 * hf + kb) * 8);
          mbar_wait(bars + 8 * (B_FE + 1 + 2 * hf), 0);
          if (hf) w_issue(&maps.wr);
#pragma unroll
          for (int kb = 0; kb < 4; kb++) u[kb] = *(const uint4*)(smem + (4 * hf + kb) * U + r * 128 + (((lane ^ r) & 7) << 4));
#pragma unroll
          for (int kb = 0; kb < 4; kb++) {
            const uint32_t uu[4] = {u[kb].x, u[kb].y, u[kb].z, u[kb].w}, vv[4] = {v[kb].x, v[kb].y, v[kb].z, v[kb].w};
#pragma unroll
            for (int e = 0; e < 4; e++) {
              uint32_t pr;
              asm("mul.rn.bf16x2 %0, %1, %2;" : "=r"(pr) : "r"(uu[e]), "r"(vv[e]));
              a += bf_lo(pr) + bf_hi(pr);
            }
          }
        }
#pragma unroll
        for (int o = 4; o; o >>= 1) a += __shfl_xor_sync(0xffffffffu, a, o);
        if ((lane & 7) == 0)
          asm volatile("st.relaxed.gpu.global.u32 [%0], %1;" ::"l"(ws->gate + rb * 128 + r),
                       "r"(pack_bf16(0.f, __fdividef(1.0f, 1.0f + __expf(-bf_lo(pack_bf16(a, 0.f))))) | tag) : "memory");
        if (t == 0) PROF_EV(18);
      }
    };
    {
      const int g = lane >> 2, q = lane & 3;
      uint32_t wf[32];
      if (!helper) {
        gate_rows();
        const uint32_t wa = sb + OFF_T + w * (3072 + 4) + q * 48 + g * 2;
#pragma unroll 1
        for (int ri = 0; ri < 2; ri++) {
          mbar_wait(bars + 8 * (B_WR + w), ri);
#pragma unroll
          for (int n2 = 0; n2 < 32 / WB; n2++) {
            uint32_t v[WB];
#pragma unroll
            for (int i = 0; i < WB; i++) {
              const int e = n2 * WB + i;
              asm volatile("ld.shared.u16 %0, [%1];" : "=r"(v[i]) : "r"(wa + ((e >> 1) & 7) * 192 + (e & 1) * (1536 + 2) + (e >> 4) * 16) : "memory");
            }
#pragma unroll
            for (int i = 0; i < WB; i++) wf[n2 * WB + i] = __byte_perm(wf[n2 * WB + i], v[i], 0x5432);
            if (WSLEEP) { asm volatile("nanosleep.u32 %0;" ::"r"(WSLEEP + (v[WB - 1] >> 16)) : "memory"); }
          }
          __syncwarp();
          if (ri == 0) w_issue(&maps.wi);
        }
        asm volatile("bar.sync 1, 128;" ::: "memory");
        if (t == 0) PROF_EV(11);
      } else {
        asm volatile("bar.sync 4, 256;" ::: "memory");
        hint_wait(&ws->cntW[0], (ep + 1) * 128u);
        const uint32_t t0 = (uint32_t)clock();
#pragma unroll 1
        for (;;) {
          uint32_t bad = 0;
#pragma unroll
          for (int i = 0; i < 32; i++) {
            const float2 v = ld_x2((const float2*)ws->Wh + (i >> 4) * 2048 + 16 * w + g + 8 * (i & 1) + 64 * q + ((i >> 1) & 7) * 256);
            wf[i] = __float_as_uint(v.x); bad |= __float_as_uint(v.y) ^ tag;
          }
          if (!__any_sync(0xffffffffu, bad & 1)) break;
          spin_guard(t0);
        }
        if (t == 0) PROF_EV(11);
      }
      if (w == 0 && elect_one()) { mbar_expect_tx(bars + 8 * B_W, 8192); bulk_load(sb + OFF_D, dtab, 8192, bars + 8 * B_W); }
      asm volatile("barrier.cluster.wait.aligned;" ::: "memory");
      mbar_wait(bars + 8 * B_W, 0);
      mbar_wait(bars + 8 * B_HX, 0);
      if (t == 0) PROF_EV(12);
      const uint32_t dd = (sb & 0x3FFFF) >> 4;
      const uint64_t dF = d128((dd + (OFF_D >> 4)) | (512u << 16)), dI = d128((dd + (OFF_D >> 4)) | (1u << 16)), dA = d128((dd + (OFF_XB >> 4)) | (512u << 16));
      float az[32];
      const int zero = blockIdx.x >> 16;
      uint32_t pf[32];
#pragma unroll
      for (int mt = 0; mt < 2; mt++) {
        wg_fence();
        if (mt == 0) mma_ss64<0, 3, 0>(az, dA, dF);
        else mma_ss64<0, 3, 2>(az, dA + 512, dF, zero);
#pragma unroll
        for (int k = 1; k < 4; k++) mma_ss64<0, 3, 1>(az, dA + (mt * 512 + k * 128), dF + k * 128);
        wg_commit();
        wg_wait<0>();
        fence_regs<0, 32>(az);
#pragma unroll
        for (int i = 0; i < 16; i++) {
          const float wr = bf_lo(wf[16 * mt + i]), wi = bf_hi(wf[16 * mt + i]);
          pf[16 * mt + i] = pack_pin(fmaf(az[2 * i], wr, -az[2 * i + 1] * wi), fmaf(az[2 * i], wi, az[2 * i + 1] * wr));
        }
      }
      if (t == 0) PROF_EV(16);
      {
        const int m = lane >> 3, r = lane & 7;
        const int sl = 2 * (m >> 1) + ((r >> 1) & 1) + 4 * (r >> 2);
        const uint32_t a0 = sb + OFF_XB + (2 * w + (m & 1)) * 2048 + sl * 64;
        uint32_t pk[16];
#pragma unroll
        for (int mt = 0; mt < 3; mt++) {
          if (mt < 2) {
            wg_fence();
            mma_rs64<0, 0, 2>(az, pf[16 * mt], pf[16 * mt + 1], pf[16 * mt + 2], pf[16 * mt + 3], dI, mt ? (int)helper : zero);
#pragma unroll
            for (int k = 1; k < 4; k++) mma_rs64<0, 0, 1>(az, pf[16 * mt + 4 * k], pf[16 * mt + 4 * k + 1], pf[16 * mt + 4 * k + 2], pf[16 * mt + 4 * k + 3], dI + k * 2);
            wg_commit();
          }
          if (mt > 0 && !helper) {
#pragma unroll
            for (int i = 0; i < 4; i++) stsm4t(a0 + ((((mt - 1) * 2 + (r & 1)) ^ (sl >> 1)) << 4) + i * 512, pk[4 * i], pk[4 * i + 1], pk[4 * i + 2], pk[4 * i + 3]);
          }
          if (mt < 2) {
            wg_wait<0>();
            fence_regs<0, 32>(az);
#pragma unroll
            for (int i = 0; i < 16; i++) pk[i] = pack_pin(az[2 * i], az[2 * i + 1]);
          }
        }
      }
      if (helper) {
#pragma unroll
        for (int i = 0; i < 16; i++) {
          const int n = i >> 1, s0 = 8 * (n >> 1) + 2 * (n & 1) + (q & 1) + 4 * (q >> 1);
          if ((n & 1) == (int)(blockIdx.x & 1)) st_u2(ws->Ts + s0 * 64 + 16 * w + g + 8 * (i & 1), pack_bf16(az[2 * i], az[2 * i + 1]), tag);
        }
        __syncwarp();
        hint_add_if(lane == 0, &ws->cntH[0]);
        if (t == 0) { ws->epoch[blockIdx.x * 8] = ep + 1; PROF_EV(13); }
      } else {
        asm volatile("fence.proxy.async.shared::cta;" ::: "memory");
        __syncwarp();
        if (elect_one()) {
          if (t == 0) PROF_EV(17);
          if (SPACE) __nanosleep(SPACE * w);
          asm volatile("cp.async.bulk.tensor.3d.global.shared::cta.bulk_group [%0, {%2, %3, %4}], [%1];" ::"l"(&maps.ts), "r"(sb + OFF_XB + w * 4096),
                       "r"(32 * kg), "r"(0), "r"(8 * tn + 2 * w) : "memory");
          bulk_done_signal(&ws->cntT[32 * j]);
          asm volatile("mbarrier.arrive.shared::cluster.b64 _, [%0];" ::"r"(mapa(bars + 8 * B_RD0, rank ^ 1)) : "memory");
          if (t == 96) PROF_EV(13);
        }
        __syncwarp();
        if (j == 0) {
          hint_wait(&ws->cntH[0], (ep + 1) * 8u);
          const uint32_t t0 = (uint32_t)clock();
          float2 v;
          do { v = ld_x2((const float2*)ws->Ts + 2 * rb * 64 + t); spin_guard(t0); } while (__any_sync(0xffffffffu, (__float_as_uint(v.y) ^ tag) & 1));
          mbar_wait(bars + 8 * B_TL, 0);
          const uint32_t u = __float_as_uint(v.x);
          *(uint16_t*)(smem + OFF_T + t * 128 + ((t & 7) << 4)) = (uint16_t)u;
          *(uint16_t*)(smem + OFF_T + t * 128 + (((t & 7) ^ 1) << 4)) = (uint16_t)(u >> 16);
          asm volatile("fence.proxy.async.shared::cta;" ::: "memory");
          __syncwarp();
          mbar_arrive_if(lane == 0, bars + 8 * B_T);
        }
      }
    }
  } else {
    asm volatile("setmaxnreg.dec.sync.aligned.u32 24;");
    auto xf_load = [&](int q) {
      const uint32_t fb = bars + 8 * (B_FX + q);
      mbar_expect_tx(fb, U + 8192);
      tma3d(sb + q * U, &maps.x, fb, 64 * q, 0, 2 * rb);
      if (q >= 4) mbar_wait(bars + 8 * (B_FE + ((q - 4) >> 1)), 0);
      tma2d(sb + OFF_XB + (q & 3) * 8192, &maps.ft, fb, 64 * q, 64 * j);
    };
    if (elect_one()) {
      if (warp == 14) {
#pragma unroll
        for (int i = 0; i < B_FT; i++) mbar_init(bars + 8 * i, 1);
        asm volatile("fence.mbarrier_init.release.cluster;" ::: "memory");
        if (!helper) {
#pragma unroll 1
          for (int n = 0; n < 2; n++) {
            const uint32_t fb = bars + 8 * (B_FA + n);
            xf_load(2 * n); xf_load(2 * n + 1);
            mbar_expect_tx(fb, U);
            tma2d(sb + OFF_RING + n * U, &maps.g64, fb, f_full, 64 * n);
            tma2d(sb + OFF_RING + n * U + 8192, &maps.u64, fb, f_full, 64 * n);
          }
        }
      } else if (warp == 15) {
#pragma unroll
        for (int i = B_FT; i < NBAR; i++) mbar_init(bars + 8 * i, i < B_EA ? 1 : i < B_T ? 2 : 4);
#pragma unroll
        for (int i = 0; i < 8; i++) mbar_expect_tx(bars + 8 * (B_Z + i), U / 2);
        asm volatile("fence.mbarrier_init.release.cluster;" ::: "memory");
        asm volatile("fence.proxy.async.shared::cta;" ::: "memory");
      }
    }
    __syncwarp();
    asm volatile("bar.arrive 0, 384;" ::: "memory");
    asm volatile("bar.arrive 4, 256;" ::: "memory");
    __syncwarp();
    asm volatile("barrier.cluster.arrive.relaxed.aligned;" ::: "memory");
    asm volatile("bar.sync 3, 128;" ::: "memory");
    if (warp == 15 && !helper) {
        mbar_wait(bars + 8 * B_FE, 0);
        const uint32_t tag = (ld_x1(&ws->epoch[blockIdx.x * 8]) + 1) & 1;
        const int c = lane >> 4, jj = 16 * blockIdx.x + (lane & 15), jm = (2048 - jj) & 2047;
        const unsigned short* pr = (const unsigned short*)w_r + 256 * c;
        const unsigned short* pi = (const unsigned short*)w_i + 256 * c;
        const float wr = 0.25f * (bf_lo(__ldg(pr + jj * 257)) + bf_lo(__ldg(pr + jm * 257)));
        const float wi = 0.25f * (bf_lo(__ldg(pi + jj * 257)) - bf_lo(__ldg(pi + jm * 257)));
        st_u2(ws->Wh + c * 2048 + jj, c ? pack_bf16(-wi, wr) : pack_bf16(wr, wi), tag);
        __syncwarp();
        hint_add_if(lane == 0, &ws->cntW[0]);
        mbar_wait(bars + 8 * B_XS, 0);
        const uint32_t t0 = (uint32_t)clock();
        uint4 v;
        do { v = ld_x4(ws->gate + rb * 128 + 4 * lane); spin_guard(t0); } while (__any_sync(0xffffffffu, ((v.x ^ tag) | (v.y ^ tag) | (v.z ^ tag) | (v.w ^ tag)) & 1));
        *(uint4*)(smem + OFF_G + lane * 16) = v;
        __syncwarp();
        mbar_arrive_if(lane < 4, bars + 8 * B_G);
      }
    if ((!helper || warp == 15) && elect_one()) {
      if (warp < 14) {
        const int p = warp - 12;
#pragma unroll 1
        for (int i = 4 + p; i < 14; i += 2) asm volatile("prefetch.tensormap [%0];" ::"l"((const char*)&maps + i * 128) : "memory");
#pragma unroll 1
        for (int n = 2; n < 31; n++) {
          const bool table = n == 4 || n >= 29;
          const bool half = n >= 17 && n < 21;
          const int q = n < 4 ? n : n < 17 ? n - 1 : n - 5;
          const CUtensorMap* m = table ? &maps.e : half ? &maps.g32 + p : &maps.g64 + p;
          const int c0 = table ? 0 : half ? f_half : f_full + 64 * (q >> 3);
          const int c1 = table ? (2 * rb + ((n & 1) ^ 1)) * 128 + 64 * p : half ? 128 * (n - 17) : 64 * (q & 7);
          const uint32_t fb = bars + 8 * (B_FA + (n & 3)), dst = sb + OFF_RING + (n & 3) * U + p * 8192;
          if (n < 4) mbar_wait(bars + 8 * (B_FE + n - 2), 0);
          else mbar_wait(bars + 8 * (B_EA + (n & 3)), ((n >> 2) & 1) ^ 1);
          tma2d(dst, m, fb, c0, c1);
          if (p == 0) mbar_expect_tx(fb, U);
        }
      } else if (warp == 15) {
        const unsigned ep1 = ld_x1(&ws->epoch[blockIdx.x * 8]) + 1;
        flag_wait(&ws->cntX[helper ? 0 : 32 * j], ep1 * 16u);
        PROF_EV(22);
        mbar_expect_tx(bars + 8 * B_HX, U);
        bulk_load(sb + OFF_XB, ws->X + (size_t)(helper ? 128 : kg * 8 + tn) * 8192, U, bars + 8 * B_HX);
        if (!helper) {
          flag_wait(&ws->cntT[32 * j], ep1 * 64u);
          PROF_EV(23);
          mbar_expect_tx(bars + 8 * B_TL, U);
          tma3d(sb + OFF_T, &maps.t, bars + 8 * B_TL, 64 * j, 0, 2 * rb);
#pragma unroll 1
          for (int i = 0; i < 3; i++) {
            flag_wait(&ws->cntP[32 * (rb * 8 + j) + i], ep1 * 8u);
            mbar_wait(bars + 8 * (B_PZ + (i == 0)), 0);
            if (i == 2) PROF_EV(26);
            mbar_expect_tx(bars + 8 * (B_HP + i), U);
            bulk_load(sb + (i ? (i - 1) * U : OFF_T), ws->part + (size_t)((rb * 8 + j) * 3 + i) * 1024, U, bars + 8 * (B_HP + i));
          }
          ws->epoch[blockIdx.x * 8] = ep1;
        }
      } else {
#pragma unroll 1
        for (int q = 4; q < 8; q++) xf_load(q);
        mbar_wait(bars + 8 * (B_FE + 2), 0);
        mbar_expect_tx(bars + 8 * B_E0, U);
        tma2d(sb + OFF_XB, &maps.e, bars + 8 * B_E0, 0, 2 * rb * 128);
        tma2d(sb + OFF_XB + 8192, &maps.e, bars + 8 * B_E0, 0, 2 * rb * 128 + 64);
#pragma unroll 1
        for (int h2 = 0; h2 < 2; h2++) {
          const int s0 = 2 * rb + h2, sg = (s0 & ~6) | ((s0 & 2) << 1) | ((s0 & 4) >> 1);
          mbar_wait(bars + 8 * (B_XS + h2), 0);
#pragma unroll 1
          for (int c = 0; c < 2; c++) {
            asm volatile("cp.async.bulk.tensor.4d.global.shared::cta.bulk_group [%0, {%2, %3, %4, %5}], [%1];" ::"l"(&maps.xs),
                         "r"(sb + OFF_XB + h2 * 8192 + c * 4096), "r"(0), "r"(sg), "r"(0), "r"(16 * j + 8 * c) : "memory");
            if (j == 0)
              asm volatile("cp.async.bulk.global.shared::cta.bulk_group [%0], [%1], 256;" ::"l"(ws->X + 128 * 8192 + c * 4096 + sg * 128),
                           "r"(sb + OFF_SP + h2 * 512 + c * 256) : "memory");
            if (SPACE && h2 + c < 2) __nanosleep(SPACE);
          }
        }
        bulk_done_signal(&ws->cntX[32 * j]);
        PROF_EV(20);
        if (rb < 8) asm volatile("cp.async.bulk.prefetch.tensor.2d.L2.global [%0, {%1, %2}];" ::"l"(&maps.g32 + (rb >> 2)), "r"(f_half), "r"(128 * (rb & 3)) : "memory");
        else asm volatile("cp.async.bulk.prefetch.tensor.2d.L2.global [%0, {%1, %2}];" ::"l"(&maps.d224), "r"(64 * (rb - 8)), "r"(224 * j) : "memory");
#pragma unroll 1
        for (int t = 0; t < 8; t++) {
          const int i = t < 3 ? t + 1 : t < 6 ? t - 2 : 0;
          const int col = 64 * (2 * ((q4 + i) & 3) + ((t < 3 || t == 6) ? 1 - rank : rank));
          const uint32_t fb = bars + 8 * (B_FT + (t & 3)), dst = sb + (t & 3) * TB;
          mbar_wait(bars + 8 * (B_ET + (t == 2 ? 3 : t & 3)), t >> 2);
          mbar_expect_tx(fb, TB);
          tma2d(dst, &maps.d224, fb, col, 224 * j);
          if (t < 2) mbar_wait(bars + 8 * (B_ET + t + 1), 0);
          tma2d(dst + 28672, &maps.ft, fb, col, 64 * j);
        }
      }
    }
  }
}

typedef CUresult (*EncodeFn)(CUtensorMap*, CUtensorMapDataType, cuuint32_t, void*, const cuuint64_t*, const cuuint64_t*, const cuuint32_t*,
                             const cuuint32_t*, CUtensorMapInterleave, CUtensorMapSwizzle, CUtensorMapL2promotion, CUtensorMapFloatOOBfill);

static void encode(EncodeFn f, CUtensorMap* m, const void* base, int rank, const cuuint64_t* dims, const cuuint64_t* strides, const cuuint32_t* box,
                   CUtensorMapSwizzle sw) {
  cuuint32_t es[5] = {1, 1, 1, 1, 1};
  f(m, CU_TENSOR_MAP_DATA_TYPE_BFLOAT16, rank, (void*)base, dims, strides, box, es, CU_TENSOR_MAP_INTERLEAVE_NONE, sw,
    CU_TENSOR_MAP_L2_PROMOTION_L2_128B, CU_TENSOR_MAP_FLOAT_OOB_FILL_NONE);
}

extern "C" void kernel_launch(void* const* d_in, const int* in_sizes, int n_in, void* d_out, int out_size) {
  (void)in_sizes; (void)n_in; (void)out_size;
  const __nv_bfloat16* x = (const __nv_bfloat16*)d_in[0];
  const __nv_bfloat16* w_r = (const __nv_bfloat16*)d_in[1];
  const __nv_bfloat16* w_i = (const __nv_bfloat16*)d_in[2];
  const __nv_bfloat16* Wg = (const __nv_bfloat16*)d_in[4];
  const __nv_bfloat16* Wu = (const __nv_bfloat16*)d_in[5];
  const __nv_bfloat16* Wd = (const __nv_bfloat16*)d_in[6];
  const __nv_bfloat16* gw = (const __nv_bfloat16*)d_in[7];

  void* fp = nullptr; cudaDriverEntryPointQueryResult qr;
  cudaGetDriverEntryPoint("cuTensorMapEncodeTiled", &fp, cudaEnableDefault, &qr);
  EncodeFn enc = (EncodeFn)fp;
  void *pFT, *pET, *pDT, *pW;
  cudaGetSymbolAddress(&pDT, g_DT); cudaGetSymbolAddress(&pW, g_work);
  void *pX = ((Work*)pW)->X, *pT = ((Work*)pW)->T;
  cudaGetSymbolAddress(&pFT, g_FT); cudaGetSymbolAddress(&pET, g_ET);

  Maps mp;
  const CUtensorMapSwizzle S128 = CU_TENSOR_MAP_SWIZZLE_128B, S64 = CU_TENSOR_MAP_SWIZZLE_64B;
  { cuuint64_t d[3] = {512, 64, 32}, s[2] = {32768, 1024}; cuuint32_t b[3] = {64, 64, 2}, b2[3] = {64, 16, 1};
    encode(enc, &mp.x, x, 3, d, s, b, S128); encode(enc, &mp.o, d_out, 3, d, s, b2, S128); }
  { cuuint64_t d[2] = {512, 512}, s[1] = {1024}; cuuint32_t b[2] = {64, 64}; encode(enc, &mp.ft, pFT, 2, d, s, b, S128); }
  { cuuint64_t d[4] = {128, 32, 2, 129}, s[3] = {256, 8192, 16384}; cuuint32_t b[4] = {128, 1, 2, 8}; encode(enc, &mp.xs, pX, 4, d, s, b, CU_TENSOR_MAP_SWIZZLE_NONE); }
  { cuuint64_t d[3] = {512, 32, 64}, s[2] = {65536, 1024}; cuuint32_t b[3] = {32, 32, 2}; encode(enc, &mp.ts, pT, 3, d, s, b, S64); }
  { cuuint64_t d[3] = {512, 64, 32}, s[2] = {1024, 65536}; cuuint32_t b[3] = {64, 64, 2}; encode(enc, &mp.t, pT, 3, d, s, b, S128); }
  { cuuint64_t d[2] = {64, 4096}, s[1] = {128}; cuuint32_t b[2] = {64, 64}; encode(enc, &mp.e, pET, 2, d, s, b, S128); }
  { cuuint64_t d[2] = {1792, 512}, s[1] = {3584}; cuuint32_t b[2] = {64, 64}, b2[2] = {32, 128};
    encode(enc, &mp.g64, Wg, 2, d, s, b, S128); encode(enc, &mp.u64, Wu, 2, d, s, b, S128);
    encode(enc, &mp.g32, Wg, 2, d, s, b2, S64); encode(enc, &mp.u32, Wu, 2, d, s, b2, S64); }
  { cuuint64_t d[2] = {512, 1792}, s[1] = {1024}; cuuint32_t b[2] = {64, 224}; encode(enc, &mp.d224, Wd, 2, d, s, b, S128); }
  { cuuint64_t d[4] = {264, 32, 8, 8}, s[3] = {32896, 512, 4112}; cuuint32_t b[4] = {24, 32, 2, 1};
    encode(enc, &mp.wr, w_r, 4, d, s, b, CU_TENSOR_MAP_SWIZZLE_NONE); encode(enc, &mp.wi, w_i, 4, d, s, b, CU_TENSOR_MAP_SWIZZLE_NONE); }

  cudaFuncSetAttribute(fused_kernel, cudaFuncAttributeMaxDynamicSharedMemorySize, SMEM_BYTES);
  fused_kernel<<<NCTA, 512, SMEM_BYTES>>>((Work*)pW, (const uint16_t*)pDT, w_r, w_i, gw, x, mp);
}
```

```cpp
#include <cuda_runtime.h>
#include <cuda_bf16.h>
#include <cuda.h>
#include <stdint.h>

namespace tbl {
constexpr double PI = 3.14159265358979323846264338327950288;
constexpr double sin_s(double x) { double t = x, s = x; for (int n = 1; n < 12; n++) { t *= -x * x / ((2 * n) * (2 * n + 1)); s += t; } return s; }
constexpr double cos_s(double x) { double t = 1, s = 1; for (int n = 1; n < 12; n++) { t *= -x * x / ((2 * n - 1) * (2 * n)); s += t; } return s; }
constexpr double cos2048(int m) {
  m &= 2047; if (m > 1024) m = 2048 - m;
  bool neg = false; if (m > 512) { m = 1024 - m; neg = true; }
  double v = (m <= 256) ? cos_s(2 * PI * m / 2048) : sin_s(2 * PI * (512 - m) / 2048);
  return neg ? -v : v;
}
constexpr uint16_t to_bf16(double v) {
  if (v == 0) return 0;
  uint16_t s = 0; if (v < 0) { s = 0x8000; v = -v; }
  int e = 0; while (v >= 2) { v /= 2; e++; } while (v < 1) { v *= 2; e--; }
  double m = (v - 1) * 128; int mi = (int)m; double fr = m - mi;
  if (fr > 0.5 || (fr == 0.5 && (mi & 1))) mi++;
  if (mi == 128) { mi = 0; e++; }
  return (uint16_t)(s | ((e + 127) << 7) | mi);
}
struct CosT { uint16_t v[2048]; constexpr CosT() : v() { for (int i = 0; i < 2048; i++) v[i] = to_bf16(cos2048(i)); } };
struct alignas(1024) FT {
  uint16_t v[512 * 512];
  constexpr FT() : v() {
    CosT c;
    for (int r = 0; r < 512; r++) {
      int k = (r >> 4) * 8 + (r & 7), e = (r >> 3) & 1;
      int mul = 4 * k, add = e ? 512 : 0;
      if (k == 0 && e == 1) { mul = 1024; add = 0; }
      for (int d = 0; d < 512; d++) v[r * 512 + d] = c.v[(d * mul + add) & 2047];
    }
  }
};
struct alignas(1024) ET {
  uint16_t v[2048 * 128];
  constexpr ET() : v() {
    CosT c;
    for (int s = 0; s < 2048; s++)
      for (int j = 0; j < 64; j++) {
        const int o = (s & 31) * 8192 + (s >> 5) * 64 + j;
        v[o] = c.v[(s * j) & 2047]; v[o + 4096] = c.v[(s * j + 512) & 2047];
      }
  }
};
struct alignas(1024) DT {
  uint16_t v[64 * 64];
  constexpr DT() : v() {
    CosT c;
    for (int r = 0; r < 64; r++)
      for (int n = 0; n < 64; n++) {
        const int sg = r >> 1, s0 = (sg & ~6) | ((sg & 2) << 1) | ((sg & 4) >> 1), e = r & 1, f = n & 1;
        const int m = 64 * s0 * (n >> 1) + (e == f ? 0 : e ? -512 : 512);
        v[r * 64 + (((n >> 3) ^ (r & 7)) << 3) + (n & 7)] = c.v[m & 2047];
      }
  }
};
}

__device__ constexpr tbl::FT g_FT = tbl::FT();
__device__ constexpr tbl::ET g_ET = tbl::ET();
__device__ constexpr tbl::DT g_DT = tbl::DT();

struct alignas(1024) Work {
  unsigned epoch[132 * 8];
  unsigned cntX[8 * 32], cntT[8 * 32], cntP[128 * 32], cntW[32], cntH[32];
  alignas(16) float gate[16 * 128];
  alignas(16) uint2 Wh[2 * 2048];
  alignas(16) uint2 Ts[32 * 64];
  alignas(1024) uint16_t X[129 * 8192];
  alignas(1024) uint16_t T[32 * 64 * 512];
  alignas(1024) uint4 part[128 * 3 * 1024];
};
__device__ Work g_work;
#define PROF_EV(i) do {} while (0)
#define PROF_CK(i) do {} while (0)

__device__ __forceinline__ uint32_t smem_u32(const void* p) { return (uint32_t)__cvta_generic_to_shared(p); }
__device__ __forceinline__ void mbar_init(uint32_t bar, uint32_t cnt) { asm volatile("mbarrier.init.shared::cta.b64 [%0], %1;" ::"r"(bar), "r"(cnt)); }
__device__ __forceinline__ void mbar_expect_tx(uint32_t bar, uint32_t bytes) { asm volatile("mbarrier.arrive.expect_tx.shared::cta.b64 _, [%0], %1;" ::"r"(bar), "r"(bytes) : "memory"); }
__device__ __forceinline__ void mbar_arrive(uint32_t bar) { asm volatile("mbarrier.arrive.shared::cta.b64 _, [%0];" ::"r"(bar) : "memory"); }
__device__ __forceinline__ bool elect_one() {
  uint32_t p;
  asm volatile("{\n.reg .pred p;\nelect.sync _|p, 0xffffffff;\nselp.u32 %0, 1, 0, p;\n}" : "=r"(p));
  return p;
}
__device__ __forceinline__ void mbar_arrive_if(bool p, uint32_t bar) {
  asm volatile("{\n.reg .pred p;\nsetp.ne.b32 p, %1, 0;\n@p mbarrier.arrive.shared::cta.b64 _, [%0];\n}" ::"r"(bar), "r"((int)p) : "memory");
}
__device__ __forceinline__ void hint_add_if(bool p, unsigned* a) {
  asm volatile("{\n.reg .pred p;\nsetp.ne.b32 p, %1, 0;\n@p red.relaxed.gpu.global.add.u32 [%0], 1;\n}" ::"l"(a), "r"((int)p) : "memory");
}
__device__ __forceinline__ bool mbar_try(uint32_t bar, uint32_t parity) {
  uint32_t ok;
  asm volatile("{\n.reg .pred p;\nmbarrier.test_wait.parity.shared::cta.b64 p, [%1], %2;\nselp.u32 %0, 1, 0, p;\n}" : "=r"(ok) : "r"(bar), "r"(parity) : "memory");
  return ok;
}
__device__ __forceinline__ void mbar_wait(uint32_t bar, uint32_t parity) {
  asm volatile(
      "{\n.reg .pred p;\n.reg .u32 n;\nmov.u32 n, 0;\n"
      "W_LOOP:\nmbarrier.try_wait.parity.shared::cta.b64 p, [%0], %1;\n@p bra W_DONE;\n"
      "add.u32 n, n, 1;\nsetp.lt.u32 p, n, 0x40000;\n@p bra W_LOOP;\ntrap;\nW_DONE:\n}" ::"r"(bar), "r"(parity) : "memory");
}
__device__ __forceinline__ void bulk_load(uint32_t dst, const void* src, uint32_t bytes, uint32_t bar) {
  asm volatile("cp.async.bulk.shared::cluster.global.mbarrier::complete_tx::bytes [%0], [%1], %2, [%3];" ::"r"(dst), "l"(src), "r"(bytes), "r"(bar) : "memory");
}
__device__ __forceinline__ void spin_guard(uint32_t t0) { if ((uint32_t)clock() - t0 > (1u << 30)) __trap(); }
__device__ __forceinline__ float2 ld_x2(const float2* p) { float2 v; asm volatile("ld.relaxed.gpu.global.v2.f32 {%0,%1}, [%2];" : "=f"(v.x), "=f"(v.y) : "l"(p) : "memory"); return v; }
__device__ __forceinline__ void st_u2(uint2* p, uint32_t a, uint32_t b) { asm volatile("st.relaxed.gpu.global.v2.u32 [%0], {%1,%2};" ::"l"(p), "r"(a), "r"(b) : "memory"); }
__device__ __forceinline__ uint32_t ld_x1(const void* p) { uint32_t v; asm volatile("ld.relaxed.gpu.global.u32 %0, [%1];" : "=r"(v) : "l"(p) : "memory"); return v; }
__device__ __forceinline__ uint4 ld_x4(const void* p) { uint4 v; asm volatile("ld.relaxed.gpu.global.v4.u32 {%0,%1,%2,%3}, [%4];" : "=r"(v.x), "=r"(v.y), "=r"(v.z), "=r"(v.w) : "l"(p) : "memory"); return v; }
__device__ __forceinline__ uint32_t mapa(uint32_t a, uint32_t cta) { uint32_t r; asm volatile("mapa.shared::cluster.u32 %0, %1, %2;" : "=r"(r) : "r"(a), "r"(cta)); return r; }
__device__ __forceinline__ void stsm4t(uint32_t a, uint32_t r0, uint32_t r1, uint32_t r2, uint32_t r3) {
  asm volatile("stmatrix.sync.aligned.m8n8.x4.trans.shared.b16 [%0], {%1,%2,%3,%4};" ::"r"(a), "r"(r0), "r"(r1), "r"(r2), "r"(r3) : "memory");
}
__device__ __forceinline__ void hint_add(unsigned* p) { asm volatile("red.relaxed.gpu.global.add.u32 [%0], 1;" ::"l"(p) : "memory"); }
__device__ __forceinline__ void hint_wait(const unsigned* p, unsigned target) {
  const uint32_t t0 = (uint32_t)clock();
  while ((int)(ld_x1(p) - target) < 0) spin_guard(t0);
}
__device__ __forceinline__ void bulk_done_signal(unsigned* p) {
  asm volatile("cp.async.bulk.commit_group;\ncp.async.bulk.wait_group 0;\nfence.proxy.async.global;" ::: "memory");
  hint_add(p);
}
__device__ __forceinline__ void flag_wait(const unsigned* p, unsigned target) {
  hint_wait(p, target);
  asm volatile("fence.proxy.async.global;" ::: "memory");
}
__device__ __forceinline__ void tma2d(uint32_t dst, const CUtensorMap* m, uint32_t bar, int c0, int c1) {
  asm volatile("cp.async.bulk.tensor.2d.shared::cluster.global.mbarrier::complete_tx::bytes [%0], [%1, {%3, %4}], [%2];" ::"r"(dst), "l"(m), "r"(bar), "r"(c0), "r"(c1) : "memory");
}
__device__ __forceinline__ void tma3d(uint32_t dst, const CUtensorMap* m, uint32_t bar, int c0, int c1, int c2) {
  asm volatile("cp.async.bulk.tensor.3d.shared::cluster.global.mbarrier::complete_tx::bytes [%0], [%1, {%3, %4, %5}], [%2];" ::"r"(dst), "l"(m), "r"(bar), "r"(c0), "r"(c1), "r"(c2) : "memory");
}
__device__ __forceinline__ void tma4d(uint32_t dst, const CUtensorMap* m, uint32_t bar, int c0, int c1, int c2, int c3) {
  asm volatile("cp.async.bulk.tensor.4d.shared::cluster.global.mbarrier::complete_tx::bytes [%0], [%1, {%3, %4, %5, %6}], [%2];" ::"r"(dst), "l"(m), "r"(bar), "r"(c0), "r"(c1), "r"(c2), "r"(c3) : "memory");
}
__device__ __forceinline__ void wg_fence() { asm volatile("wgmma.fence.sync.aligned;" ::: "memory"); }
__device__ __forceinline__ void wg_commit() { asm volatile("wgmma.commit_group.sync.aligned;" ::: "memory"); }
template <int N> __device__ __forceinline__ void wg_wait() { asm volatile("wgmma.wait_group.sync.aligned %0;" ::"n"(N) : "memory"); }
template <int O, int N, int NN> __device__ __forceinline__ void fence_regs(float (&d)[NN]) {
#pragma unroll
  for (int i = 0; i < N; i++) asm volatile("" : "+f"(d[O + i])::"memory");
}
__device__ __forceinline__ uint32_t pack_bf16(float lo, float hi) {
  uint32_t r; asm("cvt.rn.bf16x2.f32 %0, %1, %2;" : "=r"(r) : "f"(hi), "f"(lo)); return r;
}
__device__ __forceinline__ uint32_t pack_pin(float lo, float hi) {
  uint32_t r; asm volatile("cvt.rn.bf16x2.f32 %0, %1, %2;" : "=r"(r) : "f"(hi), "f"(lo) : "memory"); return r;
}
__device__ __forceinline__ uint32_t add_bf2(uint32_t a, uint32_t b) { uint32_t r; asm("add.rn.bf16x2 %0, %1, %2;" : "=r"(r) : "r"(a), "r"(b)); return r; }
__device__ __forceinline__ float bf_lo(uint32_t u) { return __uint_as_float(u << 16); }
__device__ __forceinline__ float bf_hi(uint32_t u) { return __uint_as_float(u & 0xffff0000u); }

__device__ __forceinline__ uint64_t d128(uint32_t lo) { uint64_t d; asm("mov.b64 %0, {%1, 0x40000040};" : "=l"(d) : "r"(lo)); return d; }
__device__ __forceinline__ uint64_t d64(uint32_t lo) { uint64_t d; asm("mov.b64 %0, {%1, 0x80000020};" : "=l"(d) : "r"(lo)); return d; }
template<int O,int TB,int ACC,int NN> __device__ __forceinline__ void mma_ss64(float (&d)[NN], uint64_t da, uint64_t db, int sd = 0){
  if constexpr (ACC == 1) asm volatile("wgmma.mma_async.sync.aligned.m64n64k16.f32.bf16.bf16 {%0,%1,%2,%3,%4,%5,%6,%7,%8,%9,%10,%11,%12,%13,%14,%15,%16,%17,%18,%19,%20,%21,%22,%23,%24,%25,%26,%27,%28,%29,%30,%31}, %32, %33, 1, 1, 1, %35, %34;"
   : "+f"(d[O+0]), "+f"(d[O+1]), "+f"(d[O+2]), "+f"(d[O+3]), "+f"(d[O+4]), "+f"(d[O+5]), "+f"(d[O+6]), "+f"(d[O+7]), "+f"(d[O+8]), "+f"(d[O+9]), "+f"(d[O+10]), "+f"(d[O+11]), "+f"(d[O+12]), "+f"(d[O+13]), "+f"(d[O+14]), "+f"(d[O+15]), "+f"(d[O+16]), "+f"(d[O+17]), "+f"(d[O+18]), "+f"(d[O+19]), "+f"(d[O+20]), "+f"(d[O+21]), "+f"(d[O+22]), "+f"(d[O+23]), "+f"(d[O+24]), "+f"(d[O+25]), "+f"(d[O+26]), "+f"(d[O+27]), "+f"(d[O+28]), "+f"(d[O+29]), "+f"(d[O+30]), "+f"(d[O+31])
   : "l"(da), "l"(db), "n"(TB & 1), "n"(TB >> 1));
  else if constexpr (ACC == 0) asm volatile("wgmma.mma_async.sync.aligned.m64n64k16.f32.bf16.bf16 {%0,%1,%2,%3,%4,%5,%6,%7,%8,%9,%10,%11,%12,%13,%14,%15,%16,%17,%18,%19,%20,%21,%22,%23,%24,%25,%26,%27,%28,%29,%30,%31}, %32, %33, 0, 1, 1, %35, %34;"
   : "=f"(d[O+0]), "=f"(d[O+1]), "=f"(d[O+2]), "=f"(d[O+3]), "=f"(d[O+4]), "=f"(d[O+5]), "=f"(d[O+6]), "=f"(d[O+7]), "=f"(d[O+8]), "=f"(d[O+9]), "=f"(d[O+10]), "=f"(d[O+11]), "=f"(d[O+12]), "=f"(d[O+13]), "=f"(d[O+14]), "=f"(d[O+15]), "=f"(d[O+16]), "=f"(d[O+17]), "=f"(d[O+18]), "=f"(d[O+19]), "=f"(d[O+20]), "=f"(d[O+21]), "=f"(d[O+22]), "=f"(d[O+23]), "=f"(d[O+24]), "=f"(d[O+25]), "=f"(d[O+26]), "=f"(d[O+27]), "=f"(d[O+28]), "=f"(d[O+29]), "=f"(d[O+30]), "=f"(d[O+31])
   : "l"(da), "l"(db), "n"(TB & 1), "n"(TB >> 1));
  else asm volatile("{\n.reg .pred p;\nsetp.ne.b32 p, %36, 0;\nwgmma.mma_async.sync.aligned.m64n64k16.f32.bf16.bf16 {%0,%1,%2,%3,%4,%5,%6,%7,%8,%9,%10,%11,%12,%13,%14,%15,%16,%17,%18,%19,%20,%21,%22,%23,%24,%25,%26,%27,%28,%29,%30,%31}, %32, %33, p, 1, 1, %35, %34;\n}"
   : "+f"(d[O+0]), "+f"(d[O+1]), "+f"(d[O+2]), "+f"(d[O+3]), "+f"(d[O+4]), "+f"(d[O+5]), "+f"(d[O+6]), "+f"(d[O+7]), "+f"(d[O+8]), "+f"(d[O+9]), "+f"(d[O+10]), "+f"(d[O+11]), "+f"(d[O+12]), "+f"(d[O+13]), "+f"(d[O+14]), "+f"(d[O+15]), "+f"(d[O+16]), "+f"(d[O+17]), "+f"(d[O+18]), "+f"(d[O+19]), "+f"(d[O+20]), "+f"(d[O+21]), "+f"(d[O+22]), "+f"(d[O+23]), "+f"(d[O+24]), "+f"(d[O+25]), "+f"(d[O+26]), "+f"(d[O+27]), "+f"(d[O+28]), "+f"(d[O+29]), "+f"(d[O+30]), "+f"(d[O+31])
   : "l"(da), "l"(db), "n"(TB & 1), "n"(TB >> 1), "r"(sd));
}
template<int O,int TB,int ACC,int NN> __device__ __forceinline__ void mma_rs64(float (&d)[NN], uint32_t a0, uint32_t a1, uint32_t a2, uint32_t a3, uint64_t db, int sd = 0){
  if constexpr (ACC == 1) asm volatile("wgmma.mma_async.sync.aligned.m64n64k16.f32.bf16.bf16 {%0,%1,%2,%3,%4,%5,%6,%7,%8,%9,%10,%11,%12,%13,%14,%15,%16,%17,%18,%19,%20,%21,%22,%23,%24,%25,%26,%27,%28,%29,%30,%31}, {%32,%33,%34,%35}, %36, 1, 1, 1, %37;"
   : "+f"(d[O+0]), "+f"(d[O+1]), "+f"(d[O+2]), "+f"(d[O+3]), "+f"(d[O+4]), "+f"(d[O+5]), "+f"(d[O+6]), "+f"(d[O+7]), "+f"(d[O+8]), "+f"(d[O+9]), "+f"(d[O+10]), "+f"(d[O+11]), "+f"(d[O+12]), "+f"(d[O+13]), "+f"(d[O+14]), "+f"(d[O+15]), "+f"(d[O+16]), "+f"(d[O+17]), "+f"(d[O+18]), "+f"(d[O+19]), "+f"(d[O+20]), "+f"(d[O+21]), "+f"(d[O+22]), "+f"(d[O+23]), "+f"(d[O+24]), "+f"(d[O+25]), "+f"(d[O+26]), "+f"(d[O+27]), "+f"(d[O+28]), "+f"(d[O+29]), "+f"(d[O+30]), "+f"(d[O+31])
   : "r"(a0), "r"(a1), "r"(a2), "r"(a3), "l"(db), "n"(TB));
  else if constexpr (ACC == 0) asm volatile("wgmma.mma_async.sync.aligned.m64n64k16.f32.bf16.bf16 {%0,%1,%2,%3,%4,%5,%6,%7,%8,%9,%10,%11,%12,%13,%14,%15,%16,%17,%18,%19,%20,%21,%22,%23,%24,%25,%26,%27,%28,%29,%30,%31}, {%32,%33,%34,%35}, %36, 0, 1, 1, %37;"
   : "=f"(d[O+0]), "=f"(d[O+1]), "=f"(d[O+2]), "=f"(d[O+3]), "=f"(d[O+4]), "=f"(d[O+5]), "=f"(d[O+6]), "=f"(d[O+7]), "=f"(d[O+8]), "=f"(d[O+9]), "=f"(d[O+10]), "=f"(d[O+11]), "=f"(d[O+12]), "=f"(d[O+13]), "=f"(d[O+14]), "=f"(d[O+15]), "=f"(d[O+16]), "=f"(d[O+17]), "=f"(d[O+18]), "=f"(d[O+19]), "=f"(d[O+20]), "=f"(d[O+21]), "=f"(d[O+22]), "=f"(d[O+23]), "=f"(d[O+24]), "=f"(d[O+25]), "=f"(d[O+26]), "=f"(d[O+27]), "=f"(d[O+28]), "=f"(d[O+29]), "=f"(d[O+30]), "=f"(d[O+31])
   : "r"(a0), "r"(a1), "r"(a2), "r"(a3), "l"(db), "n"(TB));
  else asm volatile("{\n.reg .pred p;\nsetp.ne.b32 p, %38, 0;\nwgmma.mma_async.sync.aligned.m64n64k16.f32.bf16.bf16 {%0,%1,%2,%3,%4,%5,%6,%7,%8,%9,%10,%11,%12,%13,%14,%15,%16,%17,%18,%19,%20,%21,%22,%23,%24,%25,%26,%27,%28,%29,%30,%31}, {%32,%33,%34,%35}, %36, p, 1, 1, %37;\n}"
   : "+f"(d[O+0]), "+f"(d[O+1]), "+f"(d[O+2]), "+f"(d[O+3]), "+f"(d[O+4]), "+f"(d[O+5]), "+f"(d[O+6]), "+f"(d[O+7]), "+f"(d[O+8]), "+f"(d[O+9]), "+f"(d[O+10]), "+f"(d[O+11]), "+f"(d[O+12]), "+f"(d[O+13]), "+f"(d[O+14]), "+f"(d[O+15]), "+f"(d[O+16]), "+f"(d[O+17]), "+f"(d[O+18]), "+f"(d[O+19]), "+f"(d[O+20]), "+f"(d[O+21]), "+f"(d[O+22]), "+f"(d[O+23]), "+f"(d[O+24]), "+f"(d[O+25]), "+f"(d[O+26]), "+f"(d[O+27]), "+f"(d[O+28]), "+f"(d[O+29]), "+f"(d[O+30]), "+f"(d[O+31])
   : "r"(a0), "r"(a1), "r"(a2), "r"(a3), "l"(db), "n"(TB), "r"(sd));
}
template<int O,int TB,int ACC,int NN> __device__ __forceinline__ void mma_ss128(float (&d)[NN], uint64_t da, uint64_t db, int sd = 0){
  if constexpr (ACC == 1) asm volatile("wgmma.mma_async.sync.aligned.m64n128k16.f32.bf16.bf16 {%0,%1,%2,%3,%4,%5,%6,%7,%8,%9,%10,%11,%12,%13,%14,%15,%16,%17,%18,%19,%20,%21,%22,%23,%24,%25,%26,%27,%28,%29,%30,%31,%32,%33,%34,%35,%36,%37,%38,%39,%40,%41,%42,%43,%44,%45,%46,%47,%48,%49,%50,%51,%52,%53,%54,%55,%56,%57,%58,%59,%60,%61,%62,%63}, %64, %65, 1, 1, 1, %67, %66;"
   : "+f"(d[O+0]), "+f"(d[O+1]), "+f"(d[O+2]), "+f"(d[O+3]), "+f"(d[O+4]), "+f"(d[O+5]), "+f"(d[O+6]), "+f"(d[O+7]), "+f"(d[O+8]), "+f"(d[O+9]), "+f"(d[O+10]), "+f"(d[O+11]), "+f"(d[O+12]), "+f"(d[O+13]), "+f"(d[O+14]), "+f"(d[O+15]), "+f"(d[O+16]), "+f"(d[O+17]), "+f"(d[O+18]), "+f"(d[O+19]), "+f"(d[O+20]), "+f"(d[O+21]), "+f"(d[O+22]), "+f"(d[O+23]), "+f"(d[O+24]), "+f"(d[O+25]), "+f"(d[O+26]), "+f"(d[O+27]), "+f"(d[O+28]), "+f"(d[O+29]), "+f"(d[O+30]), "+f"(d[O+31]), "+f"(d[O+32]), "+f"(d[O+33]), "+f"(d[O+34]), "+f"(d[O+35]), "+f"(d[O+36]), "+f"(d[O+37]), "+f"(d[O+38]), "+f"(d[O+39]), "+f"(d[O+40]), "+f"(d[O+41]), "+f"(d[O+42]), "+f"(d[O+43]), "+f"(d[O+44]), "+f"(d[O+45]), "+f"(d[O+46]), "+f"(d[O+47]), "+f"(d[O+48]), "+f"(d[O+49]), "+f"(d[O+50]), "+f"(d[O+51]), "+f"(d[O+52]), "+f"(d[O+53]), "+f"(d[O+54]), "+f"(d[O+55]), "+f"(d[O+56]), "+f"(d[O+57]), "+f"(d[O+58]), "+f"(d[O+59]), "+f"(d[O+60]), "+f"(d[O+61]), "+f"(d[O+62]), "+f"(d[O+63])
   : "l"(da), "l"(db), "n"(TB & 1), "n"(TB >> 1));
  else if constexpr (ACC == 0) asm volatile("wgmma.mma_async.sync.aligned.m64n128k16.f32.bf16.bf16 {%0,%1,%2,%3,%4,%5,%6,%7,%8,%9,%10,%11,%12,%13,%14,%15,%16,%17,%18,%19,%20,%21,%22,%23,%24,%25,%26,%27,%28,%29,%30,%31,%32,%33,%34,%35,%36,%37,%38,%39,%40,%41,%42,%43,%44,%45,%46,%47,%48,%49,%50,%51,%52,%53,%54,%55,%56,%57,%58,%59,%60,%61,%62,%63}, %64, %65, 0, 1, 1, %67, %66;"
   : "=f"(d[O+0]), "=f"(d[O+1]), "=f"(d[O+2]), "=f"(d[O+3]), "=f"(d[O+4]), "=f"(d[O+5]), "=f"(d[O+6]), "=f"(d[O+7]), "=f"(d[O+8]), "=f"(d[O+9]), "=f"(d[O+10]), "=f"(d[O+11]), "=f"(d[O+12]), "=f"(d[O+13]), "=f"(d[O+14]), "=f"(d[O+15]), "=f"(d[O+16]), "=f"(d[O+17]), "=f"(d[O+18]), "=f"(d[O+19]), "=f"(d[O+20]), "=f"(d[O+21]), "=f"(d[O+22]), "=f"(d[O+23]), "=f"(d[O+24]), "=f"(d[O+25]), "=f"(d[O+26]), "=f"(d[O+27]), "=f"(d[O+28]), "=f"(d[O+29]), "=f"(d[O+30]), "=f"(d[O+31]), "=f"(d[O+32]), "=f"(d[O+33]), "=f"(d[O+34]), "=f"(d[O+35]), "=f"(d[O+36]), "=f"(d[O+37]), "=f"(d[O+38]), "=f"(d[O+39]), "=f"(d[O+40]), "=f"(d[O+41]), "=f"(d[O+42]), "=f"(d[O+43]), "=f"(d[O+44]), "=f"(d[O+45]), "=f"(d[O+46]), "=f"(d[O+47]), "=f"(d[O+48]), "=f"(d[O+49]), "=f"(d[O+50]), "=f"(d[O+51]), "=f"(d[O+52]), "=f"(d[O+53]), "=f"(d[O+54]), "=f"(d[O+55]), "=f"(d[O+56]), "=f"(d[O+57]), "=f"(d[O+58]), "=f"(d[O+59]), "=f"(d[O+60]), "=f"(d[O+61]), "=f"(d[O+62]), "=f"(d[O+63])
   : "l"(da), "l"(db), "n"(TB & 1), "n"(TB >> 1));
  else asm volatile("{\n.reg .pred p;\nsetp.ne.b32 p, %68, 0;\nwgmma.mma_async.sync.aligned.m64n128k16.f32.bf16.bf16 {%0,%1,%2,%3,%4,%5,%6,%7,%8,%9,%10,%11,%12,%13,%14,%15,%16,%17,%18,%19,%20,%21,%22,%23,%24,%25,%26,%27,%28,%29,%30,%31,%32,%33,%34,%35,%36,%37,%38,%39,%40,%41,%42,%43,%44,%45,%46,%47,%48,%49,%50,%51,%52,%53,%54,%55,%56,%57,%58,%59,%60,%61,%62,%63}, %64, %65, p, 1, 1, %67, %66;\n}"
   : "+f"(d[O+0]), "+f"(d[O+1]), "+f"(d[O+2]), "+f"(d[O+3]), "+f"(d[O+4]), "+f"(d[O+5]), "+f"(d[O+6]), "+f"(d[O+7]), "+f"(d[O+8]), "+f"(d[O+9]), "+f"(d[O+10]), "+f"(d[O+11]), "+f"(d[O+12]), "+f"(d[O+13]), "+f"(d[O+14]), "+f"(d[O+15]), "+f"(d[O+16]), "+f"(d[O+17]), "+f"(d[O+18]), "+f"(d[O+19]), "+f"(d[O+20]), "+f"(d[O+21]), "+f"(d[O+22]), "+f"(d[O+23]), "+f"(d[O+24]), "+f"(d[O+25]), "+f"(d[O+26]), "+f"(d[O+27]), "+f"(d[O+28]), "+f"(d[O+29]), "+f"(d[O+30]), "+f"(d[O+31]), "+f"(d[O+32]), "+f"(d[O+33]), "+f"(d[O+34]), "+f"(d[O+35]), "+f"(d[O+36]), "+f"(d[O+37]), "+f"(d[O+38]), "+f"(d[O+39]), "+f"(d[O+40]), "+f"(d[O+41]), "+f"(d[O+42]), "+f"(d[O+43]), "+f"(d[O+44]), "+f"(d[O+45]), "+f"(d[O+46]), "+f"(d[O+47]), "+f"(d[O+48]), "+f"(d[O+49]), "+f"(d[O+50]), "+f"(d[O+51]), "+f"(d[O+52]), "+f"(d[O+53]), "+f"(d[O+54]), "+f"(d[O+55]), "+f"(d[O+56]), "+f"(d[O+57]), "+f"(d[O+58]), "+f"(d[O+59]), "+f"(d[O+60]), "+f"(d[O+61]), "+f"(d[O+62]), "+f"(d[O+63])
   : "l"(da), "l"(db), "n"(TB & 1), "n"(TB >> 1), "r"(sd));
}
template<int O,int TB,int ACC,int NN> __device__ __forceinline__ void mma_rs128(float (&d)[NN], uint32_t a0, uint32_t a1, uint32_t a2, uint32_t a3, uint64_t db, int sd = 0){
  if constexpr (ACC == 1) asm volatile("wgmma.mma_async.sync.aligned.m64n128k16.f32.bf16.bf16 {%0,%1,%2,%3,%4,%5,%6,%7,%8,%9,%10,%11,%12,%13,%14,%15,%16,%17,%18,%19,%20,%21,%22,%23,%24,%25,%26,%27,%28,%29,%30,%31,%32,%33,%34,%35,%36,%37,%38,%39,%40,%41,%42,%43,%44,%45,%46,%47,%48,%49,%50,%51,%52,%53,%54,%55,%56,%57,%58,%59,%60,%61,%62,%63}, {%64,%65,%66,%67}, %68, 1, 1, 1, %69;"
   : "+f"(d[O+0]), "+f"(d[O+1]), "+f"(d[O+2]), "+f"(d[O+3]), "+f"(d[O+4]), "+f"(d[O+5]), "+f"(d[O+6]), "+f"(d[O+7]), "+f"(d[O+8]), "+f"(d[O+9]), "+f"(d[O+10]), "+f"(d[O+11]), "+f"(d[O+12]), "+f"(d[O+13]), "+f"(d[O+14]), "+f"(d[O+15]), "+f"(d[O+16]), "+f"(d[O+17]), "+f"(d[O+18]), "+f"(d[O+19]), "+f"(d[O+20]), "+f"(d[O+21]), "+f"(d[O+22]), "+f"(d[O+23]), "+f"(d[O+24]), "+f"(d[O+25]), "+f"(d[O+26]), "+f"(d[O+27]), "+f"(d[O+28]), "+f"(d[O+29]), "+f"(d[O+30]), "+f"(d[O+31]), "+f"(d[O+32]), "+f"(d[O+33]), "+f"(d[O+34]), "+f"(d[O+35]), "+f"(d[O+36]), "+f"(d[O+37]), "+f"(d[O+38]), "+f"(d[O+39]), "+f"(d[O+40]), "+f"(d[O+41]), "+f"(d[O+42]), "+f"(d[O+43]), "+f"(d[O+44]), "+f"(d[O+45]), "+f"(d[O+46]), "+f"(d[O+47]), "+f"(d[O+48]), "+f"(d[O+49]), "+f"(d[O+50]), "+f"(d[O+51]), "+f"(d[O+52]), "+f"(d[O+53]), "+f"(d[O+54]), "+f"(d[O+55]), "+f"(d[O+56]), "+f"(d[O+57]), "+f"(d[O+58]), "+f"(d[O+59]), "+f"(d[O+60]), "+f"(d[O+61]), "+f"(d[O+62]), "+f"(d[O+63])
   : "r"(a0), "r"(a1), "r"(a2), "r"(a3), "l"(db), "n"(TB));
  else if constexpr (ACC == 0) asm volatile("wgmma.mma_async.sync.aligned.m64n128k16.f32.bf16.bf16 {%0,%1,%2,%3,%4,%5,%6,%7,%8,%9,%10,%11,%12,%13,%14,%15,%16,%17,%18,%19,%20,%21,%22,%23,%24,%25,%26,%27,%28,%29,%30,%31,%32,%33,%34,%35,%36,%37,%38,%39,%40,%41,%42,%43,%44,%45,%46,%47,%48,%49,%50,%51,%52,%53,%54,%55,%56,%57,%58,%59,%60,%61,%62,%63}, {%64,%65,%66,%67}, %68, 0, 1, 1, %69;"
   : "=f"(d[O+0]), "=f"(d[O+1]), "=f"(d[O+2]), "=f"(d[O+3]), "=f"(d[O+4]), "=f"(d[O+5]), "=f"(d[O+6]), "=f"(d[O+7]), "=f"(d[O+8]), "=f"(d[O+9]), "=f"(d[O+10]), "=f"(d[O+11]), "=f"(d[O+12]), "=f"(d[O+13]), "=f"(d[O+14]), "=f"(d[O+15]), "=f"(d[O+16]), "=f"(d[O+17]), "=f"(d[O+18]), "=f"(d[O+19]), "=f"(d[O+20]), "=f"(d[O+21]), "=f"(d[O+22]), "=f"(d[O+23]), "=f"(d[O+24]), "=f"(d[O+25]), "=f"(d[O+26]), "=f"(d[O+27]), "=f"(d[O+28]), "=f"(d[O+29]), "=f"(d[O+30]), "=f"(d[O+31]), "=f"(d[O+32]), "=f"(d[O+33]), "=f"(d[O+34]), "=f"(d[O+35]), "=f"(d[O+36]), "=f"(d[O+37]), "=f"(d[O+38]), "=f"(d[O+39]), "=f"(d[O+40]), "=f"(d[O+41]), "=f"(d[O+42]), "=f"(d[O+43]), "=f"(d[O+44]), "=f"(d[O+45]), "=f"(d[O+46]), "=f"(d[O+47]), "=f"(d[O+48]), "=f"(d[O+49]), "=f"(d[O+50]), "=f"(d[O+51]), "=f"(d[O+52]), "=f"(d[O+53]), "=f"(d[O+54]), "=f"(d[O+55]), "=f"(d[O+56]), "=f"(d[O+57]), "=f"(d[O+58]), "=f"(d[O+59]), "=f"(d[O+60]), "=f"(d[O+61]), "=f"(d[O+62]), "=f"(d[O+63])
   : "r"(a0), "r"(a1), "r"(a2), "r"(a3), "l"(db), "n"(TB));
  else asm volatile("{\n.reg .pred p;\nsetp.ne.b32 p, %70, 0;\nwgmma.mma_async.sync.aligned.m64n128k16.f32.bf16.bf16 {%0,%1,%2,%3,%4,%5,%6,%7,%8,%9,%10,%11,%12,%13,%14,%15,%16,%17,%18,%19,%20,%21,%22,%23,%24,%25,%26,%27,%28,%29,%30,%31,%32,%33,%34,%35,%36,%37,%38,%39,%40,%41,%42,%43,%44,%45,%46,%47,%48,%49,%50,%51,%52,%53,%54,%55,%56,%57,%58,%59,%60,%61,%62,%63}, {%64,%65,%66,%67}, %68, p, 1, 1, %69;\n}"
   : "+f"(d[O+0]), "+f"(d[O+1]), "+f"(d[O+2]), "+f"(d[O+3]), "+f"(d[O+4]), "+f"(d[O+5]), "+f"(d[O+6]), "+f"(d[O+7]), "+f"(d[O+8]), "+f"(d[O+9]), "+f"(d[O+10]), "+f"(d[O+11]), "+f"(d[O+12]), "+f"(d[O+13]), "+f"(d[O+14]), "+f"(d[O+15]), "+f"(d[O+16]), "+f"(d[O+17]), "+f"(d[O+18]), "+f"(d[O+19]), "+f"(d[O+20]), "+f"(d[O+21]), "+f"(d[O+22]), "+f"(d[O+23]), "+f"(d[O+24]), "+f"(d[O+25]), "+f"(d[O+26]), "+f"(d[O+27]), "+f"(d[O+28]), "+f"(d[O+29]), "+f"(d[O+30]), "+f"(d[O+31]), "+f"(d[O+32]), "+f"(d[O+33]), "+f"(d[O+34]), "+f"(d[O+35]), "+f"(d[O+36]), "+f"(d[O+37]), "+f"(d[O+38]), "+f"(d[O+39]), "+f"(d[O+40]), "+f"(d[O+41]), "+f"(d[O+42]), "+f"(d[O+43]), "+f"(d[O+44]), "+f"(d[O+45]), "+f"(d[O+46]), "+f"(d[O+47]), "+f"(d[O+48]), "+f"(d[O+49]), "+f"(d[O+50]), "+f"(d[O+51]), "+f"(d[O+52]), "+f"(d[O+53]), "+f"(d[O+54]), "+f"(d[O+55]), "+f"(d[O+56]), "+f"(d[O+57]), "+f"(d[O+58]), "+f"(d[O+59]), "+f"(d[O+60]), "+f"(d[O+61]), "+f"(d[O+62]), "+f"(d[O+63])
   : "r"(a0), "r"(a1), "r"(a2), "r"(a3), "l"(db), "n"(TB), "r"(sd));
}

#define NEARLY 0
#define XAHEAD 3
#define HEADN 6
#define WBATCH 1
#define WB 8
#define WSLEEP 20
#define XSPREAD 4
#define NOSEND 0
#define MSPLIT 3
#define PFALL 1
#define L2PF 1
#define STAG 0
#define EPF 2
#define XNB 2
#define FNB 0
#define GNB 0
#define TH 4
#define PF0 4
#define FSPLIT 1
#define MGLU 1
#define SPC 2
#define TL 14
#define SPACE 40
#define WPF 1
#define WAFTER 7
#define WPACE 0
#define GATE_AT 4
#define TPACE 40
#define PFMODE 0
#define MAPMODE 1
template <int V> struct IC { static constexpr int value = V; };
struct Maps { CUtensorMap x, ft, g64, u64, e, wr, wi, xs, ts, t, g32, u32, d224, o; };

constexpr int NCTA = 130;
constexpr int U = 16384;
constexpr int TB = 36864;
constexpr int OFF_RING = 8 * U, OFF_Z = 12 * U, OFF_XB = 12 * U, OFF_T = 13 * U, OFF_D = OFF_T;
constexpr int OFF_BAR = 14 * U, OFF_SP = OFF_BAR + 512, OFF_G = OFF_SP + 1024 + 128;
constexpr int SMEM_BYTES = OFF_G + 512;
constexpr int B_FX = 0, B_FA = 8, B_FT = 12, B_Z = 16, B_W = 24, B_HX = 25, B_TL = 26, B_HP = 27, B_WR = 30, B_E0 = 34;
constexpr int B_EA = 35, B_ET = 39, B_PZ = 43, B_RDY = 45, B_FE = 46;
constexpr int B_T = 50, B_XS = 51, B_G = 53, B_RD0 = 54, NBAR = 55;
__host__ __device__ constexpr int rslot(int n) { return n & 3; }
__host__ __device__ constexpr int rpar(int n) { return (n >> 2) & 1; }

__global__ void __cluster_dims__(2, 1, 1) __launch_bounds__(512, 1)
fused_kernel(Work* __restrict__ ws, const uint16_t* __restrict__ dtab, const __nv_bfloat16* __restrict__ w_r, const __nv_bfloat16* __restrict__ w_i,
             const __nv_bfloat16* __restrict__ gate_w, const __nv_bfloat16* __restrict__ x, const __grid_constant__ Maps maps) {
  extern __shared__ __align__(1024) uint8_t smem[];
  if (threadIdx.x < 32 && elect_one()) {
#pragma unroll
    for (int i = 0; i < PF0; i++) asm volatile("prefetch.tensormap [%0];" ::"l"((const char*)&maps + i * 128) : "memory");
  }
  const uint32_t sb = smem_u32(smem);
  const uint32_t bars = sb + OFF_BAR;
  const int tid = threadIdx.x, lane = tid & 31;
  const int warp = __shfl_sync(0xffffffffu, tid >> 5, 0);
  const bool helper = blockIdx.x >= 128;
  const int cl = (blockIdx.x >> 1) & 63, rank = blockIdx.x & 1;
  const int q4 = (cl & 1) | ((cl >> 2) & 2), rb = ((cl >> 1) & 3) | ((cl >> 4) << 2);
  const int j = 2 * q4 + rank;
  const int f_full = 448 * q4 + (rank ? 256 : 0);
  const int f_half = 448 * q4 + (rank ? 224 : 192);
  const int kg = 2 * j + (rb >> 3), tn = rb & 7;

  if (tid == 64) { PROF_EV(0); PROF_CK(40); }
  if (warp < 8) {
    if (!helper && tid < 32) {
      const int r = 16 * j + (tid & 15);
      asm volatile("prefetch.global.L2 [%0];" ::"l"(x + (size_t)(2 * rb + (r >> 6) + 32 * (r & 63)) * 512 + 64 * (tid >> 4)));
    }
    asm volatile("barrier.cluster.arrive.relaxed.aligned;" ::: "memory");
    asm volatile("setmaxnreg.inc.sync.aligned.u32 192;");
    if (!helper) {
      const int wg = warp >> 2, w = warp & 3, g = lane >> 2;
      const bool elect = (tid & 127) == 0;
      float cX[32], cA[64], cB[64], cC[64], ci[64], ct[64];
      const int zero = blockIdx.x >> 16;
      uint32_t h[56], yf[16];
      const uint32_t d0 = (sb & 0x3FFFF) >> 4;
      const uint32_t dK = d0 | (1u << 16), dN = d0 | (512u << 16);
      const uint32_t dX = dK + wg * 512;
      constexpr uint32_t RING = OFF_RING >> 4;
      auto waitA = [&](int n) { mbar_wait(bars + 8 * (B_FA + rslot(n)), rpar(n)); };
      auto freeA = [&](int n) { mbar_arrive_if(elect, bars + 8 * (B_EA + rslot(n))); };
      auto nop = [] {};

      asm volatile("bar.sync 0, 384;" ::: "memory");
#pragma unroll 1
      for (int i = 0; i < 4; i++) {
        const uint64_t dx = d128(dX + i * 2048), df = d128(dK + (OFF_XB >> 4) + (i & 1) * 1024);
        mbar_wait(bars + 8 * (B_FX + 2 * i), 0);
        wg_fence();
        mma_ss64<0, 0, 2>(cX, df, dx, i);
        mma_ss64<0, 0, 1>(cX, df + 2, dx + 2);
        wg_commit(); wg_wait<1>();
        mbar_arrive_if(elect && i, bars + 8 * (B_EA + rslot(i - 1)));
        mma_ss64<0, 0, 1>(cX, df + 4, dx + 4);
        mma_ss64<0, 0, 1>(cX, df + 6, dx + 6);
        if (i == 0 && tid == 0) PROF_EV(1);
        mbar_wait(bars + 8 * (B_FX + 2 * i + 1), 0);
        wg_fence();
#pragma unroll
        for (int k = 0; k < 4; k++) mma_ss64<0, 0, 1>(cX, df + (512 + k * 2), dx + (1024 + k * 2));
        wg_commit();
        waitA(i);
        wg_fence();
        const uint64_t da = d128(dX + i * 1024), db = d128(dN + RING + i * 1024);
        mma_ss128<0, 1, 2>(cA, da, db, i);
        wg_commit(); wg_wait<1>();
        mbar_arrive_if(elect, bars + 8 * (B_FE + i));
#pragma unroll
        for (int k = 1; k < 4; k++) mma_ss128<0, 1, 1>(cA, da + k * 2, db + k * 128);
        wg_commit();
      }
      fence_regs<0, 32>(cX);
#pragma unroll
      for (int e = 0; e < 16; e++) yf[e] = pack_pin(cX[2 * e], cX[2 * e + 1]);
      if (tid == 0) { PROF_EV(2); PROF_CK(42); }
      {
        waitA(4); mbar_wait(bars + 8 * B_E0, 0);
        const uint64_t de = d128(dN + (wg ? RING : OFF_XB >> 4));
        wg_fence();
        mma_rs128<0, 1, 0>(cB, yf[0], yf[1], yf[2], yf[3], de);
        wg_commit();
        wg_wait<1>();
        freeA(3);
#pragma unroll
        for (int k = 1; k < 4; k++) mma_rs128<0, 1, 1>(cB, yf[4 * k], yf[4 * k + 1], yf[4 * k + 2], yf[4 * k + 3], de + k * 128);
        wg_commit();
      }
      bool rel = false;
      auto acquire = [&](int n) {
        rel = elect;
        if (!mbar_try(bars + 8 * (B_FA + rslot(n)), rpar(n))) { wg_wait<0>(); freeA(n - 1); rel = false; waitA(n); }
      };
      auto freeP = [&](int n) { mbar_arrive_if(rel, bars + 8 * (B_EA + rslot(n - 1))); };
      auto ffn_step = [&](auto first, auto split, float (&acc)[64], int n, int kb, auto done, auto work) {
        constexpr int SPLIT = decltype(split)::value;
        acquire(n);
        wg_fence();
        const uint64_t dx = d128(dX + kb * 1024), db = d128(dN + RING + rslot(n) * 1024);
        mma_ss128<0, 1, decltype(first)::value>(acc, dx, db, kb);
#pragma unroll
        for (int k = 1; k < SPLIT; k++) mma_ss128<0, 1, 1>(acc, dx + k * 2, db + k * 128);
        wg_commit();
        work();
        wg_wait<1>();
        freeP(n);
        done();
        if (SPLIT < 4) {
          wg_fence();
#pragma unroll
          for (int k = SPLIT; k < 4; k++) mma_ss128<0, 1, 1>(acc, dx + k * 2, db + k * 128);
          wg_commit();
        }
      };
      {
        const int s0 = 2 * rb + wg, kr = 2 * ((s0 & 1) | ((s0 & 4) >> 1));
        const int m = lane >> 3, r = lane & 7;
        const uint32_t a0 = sb + OFF_XB + wg * 8192 + (((w >> 1) * 8 + (m >> 1)) * 2 + (w & 1)) * 256 + (m & 1) * 128 + ((r ^ (kr + (m & 1))) << 4);
        ffn_step(IC<1>(), IC<4>(), cA, 5, 4, [&] { fence_regs<0, 64>(cB); }, nop);
        asm volatile("bar.sync 5, 256;" ::: "memory");
        auto stage = [&](int i) {
          stsm4t(a0 + i * 1024, pack_bf16(cB[8 * i] - cB[34 + 8 * i], cB[8 * i + 1] - cB[35 + 8 * i]),
                 pack_bf16(cB[32 + 8 * i] + cB[8 * i + 2], cB[33 + 8 * i] + cB[8 * i + 3]),
                 pack_bf16(cB[8 * i + 4] - cB[38 + 8 * i], cB[8 * i + 5] - cB[39 + 8 * i]),
                 pack_bf16(cB[36 + 8 * i] + cB[8 * i + 6], cB[37 + 8 * i] + cB[8 * i + 7]));
          if (j == 0 && w == 0) {
            const uint32_t a1 = r ? sb + OFF_SP + 1024 : sb + OFF_SP + wg * 512 + (m & 1) * 256 + (m >> 1) * 128;
#pragma unroll
            for (int n = 2 * i; n < 2 * i + 2; n++)
              asm volatile("stmatrix.sync.aligned.m8n8.x4.shared.b16 [%0], {%1,%2,%3,%4};" ::"r"(a1 + ((n ^ (kr + (m >> 1)) ^ r) << 4)),
                           "r"(pack_bf16(cB[4 * n], cB[4 * n + 1])), "r"(pack_bf16(cB[4 * n + 2], cB[4 * n + 3])),
                           "r"(pack_bf16(cB[32 + 4 * n], cB[33 + 4 * n])), "r"(pack_bf16(cB[34 + 4 * n], cB[35 + 4 * n])) : "memory");
          }
        };
        auto publish = [&] {
          asm volatile("fence.proxy.async.shared::cta;" ::: "memory");
          __syncwarp();
          mbar_arrive_if(lane == 0, bars + 8 * (B_XS + wg));
          if (tid == 0) PROF_EV(3);
        };
        stage(0);
        ffn_step(IC<1>(), IC<FSPLIT>(), cA, 6, 5, nop, nop);
        stage(1);
        ffn_step(IC<1>(), IC<FSPLIT>(), cA, 7, 6, nop, nop);
        stage(2);
        ffn_step(IC<1>(), IC<2>(), cA, 8, 7, [&] { stage(3); }, nop);
        publish();
      }
      float g0 = 0.f, g1 = 0.f;
      uint32_t tag = 0;
      uint32_t ob[2] = {0, 0};
      auto glu = [&](auto& acc, int half, int ho, int i0, int i1) {
#pragma unroll
        for (int i = i0; i < i1; i++)
          asm volatile("{\n.reg .b32 a, b;\ncvt.rn.relu.bf16x2.f32 a, %2, %1;\ncvt.rn.bf16x2.f32 b, %4, %3;\nmul.rn.bf16x2 a, a, b;\nmul.rn.bf16x2 %0, a, %5;\n}"
                       : "=r"(h[ho + i]) : "f"(acc[2 * i]), "f"(acc[2 * i + 1]), "f"(acc[half + 2 * i]), "f"(acc[half + 1 + 2 * i]), "r"(ob[i & 1]) : "memory");
      };
      ffn_step(IC<2>(), IC<1>(), cB, 9, zero, nop, nop);
#pragma unroll 1
      for (int kb = 1; kb < 8; kb++)
        ffn_step(IC<1>(), IC<FSPLIT>(), cB, 9 + kb, kb, nop, [&] {
          if (kb == 4 + 2 * wg) {
            mbar_wait(bars + 8 * B_G, 0);
            const uint32_t gb0 = *(const uint32_t*)(smem + OFF_G + (wg * 64 + w * 16 + g) * 4), gb1 = *(const uint32_t*)(smem + OFF_G + (wg * 64 + w * 16 + g + 8) * 4);
            tag = gb0 & 1; g0 = __uint_as_float(gb0 & ~1u); g1 = __uint_as_float(gb1 & ~1u);
            ob[0] = pack_bf16(1.0f - g0, 1.0f - g0); ob[1] = pack_bf16(1.0f - g1, 1.0f - g1);
            glu(cA, 32, 0, 0, 16);
          }
        });
      if (tid == 0) { PROF_EV(4); PROF_CK(43); }
      auto m_step = [&](auto first, int i) {
        acquire(17 + i);
        wg_fence();
        const uint64_t dx = d128(dX + i * 2048), dm = d64(dN + RING + rslot(17 + i) * 1024);
        mma_ss64<0, 1, decltype(first)::value>(ct, dx, dm);
#pragma unroll
        for (int k = 1; k < MSPLIT; k++) mma_ss64<0, 1, 1>(ct, dx + ((k >> 2) * 1024 + (k & 3) * 2), dm + k * 64);
        wg_commit();
        wg_wait<1>();
        freeP(17 + i);
        wg_fence();
#pragma unroll
        for (int k = MSPLIT; k < 8; k++) mma_ss64<0, 1, 1>(ct, dx + ((k >> 2) * 1024 + (k & 3) * 2), dm + k * 64);
        wg_commit();
      };
      m_step(IC<0>(), 0);
#pragma unroll 1
      for (int i = 1; i < 5; i++) {
        if (i == 1 + 2 * wg) glu(cB, 32, 16, 0, 16);
        if (i < 4) m_step(IC<1>(), i);
      }
      if (tid == 0) { PROF_EV(5); PROF_CK(44); }
      ffn_step(IC<0>(), IC<1>(), cC, 21, 0, nop, nop);
#pragma unroll 1
      for (int kb = 1; kb < 8; kb++)
        ffn_step(IC<1>(), IC<FSPLIT>(), cC, 21 + kb, kb, [&] { mbar_arrive_if(elect && !(kb & 1), bars + 8 * (B_ET + (kb >> 1) - 1)); }, [&] {
          if (kb == 1 + wg) glu(ct, 16, 48, 0, 8);
        });

      auto twait = [&](uint32_t bar, uint32_t par, int) { mbar_wait(bar, par); };
      const int fo = warp * 128 + lane;
      auto fetch = [&](uint4 (&pv)[4], int z) {
        twait(bars + 8 * (z < 4 ? B_Z + 2 * z + wg : B_HP + z - 4), 0, 8 + z);
        const uint8_t* src = smem + (z < 4 ? OFF_Z - z * U : z == 4 ? OFF_T : (z - 5) * U) + fo * 16;
#pragma unroll
        for (int i = 0; i < 4; i++) pv[i] = *(const uint4*)(src + i * 512);
      };
      auto check = [&](uint4 (&pv)[4], int z) {
        const uint32_t t0 = (uint32_t)clock();
        while (__any_sync(0xffffffffu, ((pv[0].x ^ tag) | (pv[1].x ^ tag) | (pv[2].x ^ tag) | (pv[3].x ^ tag)) & 1)) {
#pragma unroll
          for (int i = 0; i < 4; i++) pv[i] = ld_x4(ws->part + (size_t)((rb * 8 + j) * 3 + z - 4) * 1024 + fo + i * 32);
          spin_guard(t0);
        }
#pragma unroll
        for (int i = 0; i < 4; i++) pv[i].x &= ~1u;
      };
      const uint32_t peerZ = mapa(sb + OFF_Z + fo * 16, rank ^ 1), peerB = mapa(bars + 8 * (B_Z + wg), rank ^ 1);
      auto tile_mma = [&](auto off, int t, int k0, int k1, int init) {
        constexpr int O = decltype(off)::value;
        const uint64_t db = d128(dN + (t & 3) * (TB >> 4)), dw = db + rank * 256, dm = db + (rank ? 0 : 1536);
#pragma unroll
        for (int k = k0; k < k1; k++) {
          if (k == 0) mma_rs64<O, 1, 2>(ct, h[0], h[1], h[2], h[3], dw, init);
          else if (k < 14) mma_rs64<O, 1, 1>(ct, h[4 * k], h[4 * k + 1], h[4 * k + 2], h[4 * k + 3], k < 12 ? dw + k * 128 : dm + (k - 12) * 128);
          else mma_rs64<O, 1, 1>(ct, yf[4 * k - 56], yf[4 * k - 55], yf[4 * k - 54], yf[4 * k - 53], db + k * 128);
        }
      };
      uint4 pv[4] = {};
      auto tile = [&](auto off, int t) {
        constexpr int P = 32 - decltype(off)::value;
        const bool grid = t >= 4 && t < 7, pre = t >= 3 && t != 6;
        const int zo = grid ? t - 4 : t == 7 ? 3 : t - 1, z = t - 3;
        const int owner = rb * 8 + 2 * ((q4 + zo + 1) & 3) + rank;
        uint4* dst = ws->part + (size_t)(owner * 3 + zo) * 1024 + fo;
        const uint32_t src = sb + (z < 4 ? OFF_Z - z * U : OFF_T) + fo * 16;
        twait(bars + 8 * (B_FT + (t & 3)), t >> 2, t);
        wg_fence();
        tile_mma(off, t, 0, TH, zero);
        wg_commit();
        wg_wait<1>();
        mbar_arrive_if(elect && t < 6, bars + 8 * (B_ET + t - 1));
        if (t < 3) twait(bars + 8 * (t == 1 ? B_RD0 : B_RDY), 0, 14 + t);
        fence_regs<P, 32>(ct);
#pragma unroll
        for (int i = 0; i < 4; i++) {
          pv[i].x = (add_bf2(pv[i].x, pack_bf16(ct[P + 8 * i], ct[P + 8 * i + 1])) & ~(uint32_t)grid) | (tag & grid);
          pv[i].y = add_bf2(pv[i].y, pack_bf16(ct[P + 8 * i + 2], ct[P + 8 * i + 3]));
          pv[i].z = add_bf2(pv[i].z, pack_bf16(ct[P + 8 * i + 4], ct[P + 8 * i + 5]));
          pv[i].w = add_bf2(pv[i].w, pack_bf16(ct[P + 8 * i + 6], ct[P + 8 * i + 7]));
        }
        if (grid) {
#pragma unroll
          for (int i = 0; i < 4; i++)
            asm volatile("st.relaxed.gpu.global.v4.u32 [%0], {%1,%2,%3,%4};" ::"l"(dst + i * 32), "r"(pv[i].x), "r"(pv[i].y), "r"(pv[i].z), "r"(pv[i].w) : "memory");
          hint_add_if(lane == 0, &ws->cntP[32 * owner + 8 * zo]);
        }
#pragma unroll
        for (int i = 0; i < 4; i++) {
          if (!grid)
            asm volatile("st.async.weak.shared::cluster.mbarrier::complete_tx::bytes.v4.b32 [%0], {%2,%3,%4,%5}, [%1];" ::"r"(peerZ - zo * U + i * 512),
                         "r"(peerB + 16 * zo), "r"(pv[i].x), "r"(pv[i].y), "r"(pv[i].z), "r"(pv[i].w) : "memory");
          wg_fence();
          tile_mma(off, t, TH + SPC * i, i < 3 ? TH + SPC * i + SPC : TL, 0);
        }
        wg_commit();
        if (pre) twait(bars + 8 * (z < 4 ? B_Z + 2 * z + wg : B_HP), 0, 8 + z);
        wg_fence();
#pragma unroll
        for (int i = 0; i < 4; i++) {
          asm volatile("{\n.reg .pred p;\nsetp.ne.b32 p, %5, 0;\nmov.b32 %0, 0;\nmov.b32 %1, 0;\nmov.b32 %2, 0;\nmov.b32 %3, 0;\n@p ld.shared.v4.u32 {%0,%1,%2,%3}, [%4];\n}"
                       : "=r"(pv[i].x), "=r"(pv[i].y), "=r"(pv[i].z), "=r"(pv[i].w) : "r"(src + i * 512), "r"((int)pre) : "memory");
          tile_mma(off, t, TL + i, i < 3 ? TL + 1 + i : 18, 0);
        }
        wg_commit();
      };
      asm volatile("barrier.cluster.wait.aligned;" ::: "memory");
      twait(bars + 8 * B_FT, 0, 0);
      wg_fence();
      tile_mma(IC<0>(), 0, 0, 5, zero);
      wg_commit();
      wg_wait<1>();
      mbar_arrive_if(elect, bars + 8 * (B_ET + 3));
      glu(cC, 32, 32, 0, 8);
      waitA(29 + wg);
      wg_fence();
      tile_mma(IC<0>(), 0, 5, 8, 0);
      tile_mma(IC<0>(), 0, 12, 14, 0);
      wg_commit();
      glu(cC, 32, 32, 8, 16);
      if (tid == 0) PROF_EV(6);
      if (tid == 128) PROF_EV(27);
      mbar_wait(bars + 8 * (j == 0 ? B_T : B_TL), 0);
      if (tid == 0) { PROF_EV(7); PROF_CK(45); }
      wg_fence();
      {
        const uint64_t dt = d128(dN + (OFF_T >> 4) + wg * 512), de = d128(dK + RING + (1 + wg) * 1024);
        mma_ss64<0, 1, 0>(ci, de, dt);
        mma_ss64<32, 1, 0>(ci, de + 512, dt);
#pragma unroll
        for (int k = 1; k < 4; k++) {
          mma_ss64<0, 1, 1>(ci, de + k * 2, dt + k * 128);
          mma_ss64<32, 1, 1>(ci, de + (512 + k * 2), dt + k * 128);
        }
        wg_commit();
      }
      tile_mma(IC<0>(), 0, 8, 12, 0);
      wg_commit();
      wg_wait<1>();
      if (elect) asm volatile("mbarrier.arrive.shared::cluster.b64 _, [%0];" ::"r"(mapa(bars + 8 * B_RDY, rank ^ 1)) : "memory");
      mbar_arrive_if(elect, bars + 8 * (B_PZ + 1));
      fence_regs<0, 64>(ci);
#pragma unroll
      for (int i = 0; i < 16; i++) {
        const float gg = ((i & 1) ? g1 : g0) * (2.0f / (2048.0f * 512.0f));
        if (i & 2) yf[i] = pack_pin((ci[2 * i] - ci[28 + 2 * i]) * gg, (ci[2 * i + 1] - ci[29 + 2 * i]) * gg);
        else yf[i] = pack_pin((ci[2 * i] + ci[36 + 2 * i]) * gg, (ci[2 * i + 1] + ci[37 + 2 * i]) * gg);
      }
      wg_fence();
      tile_mma(IC<0>(), 0, 14, 18, 0);
      wg_commit();
      if (tid == 0) PROF_EV(8);
      if (tid == 128) PROF_EV(28);
#pragma unroll 1
      for (int t = 1;; t += 2) {
        tile(IC<32>(), t);
        if (t == 7) break;
        tile(IC<0>(), t + 1);
      }
      if (tid == 0) { PROF_EV(9); PROF_CK(46); }
      if (tid == 128) PROF_EV(29);
      {
        uint4 p1[4], p2[4];
        auto acc4 = [&](uint4 (&d)[4], const uint4 (&a)[4]) {
#pragma unroll
          for (int i = 0; i < 4; i++) { d[i].x = add_bf2(d[i].x, a[i].x); d[i].y = add_bf2(d[i].y, a[i].y); d[i].z = add_bf2(d[i].z, a[i].z); d[i].w = add_bf2(d[i].w, a[i].w); }
        };
        fetch(p1, 5);
        fetch(p2, 3);
        if (tid == 0) PROF_EV(25);
        check(pv, 4); check(p1, 5);
        acc4(pv, p1); acc4(pv, p2);
        wg_wait<0>();
        fence_regs<32, 32>(ct);
#pragma unroll
        for (int i = 0; i < 4; i++) {
          pv[i].x = pack_pin(ct[32 + 8 * i] + bf_lo(pv[i].x), ct[33 + 8 * i] + bf_hi(pv[i].x)); pv[i].y = pack_pin(ct[34 + 8 * i] + bf_lo(pv[i].y), ct[35 + 8 * i] + bf_hi(pv[i].y));
          pv[i].z = pack_pin(ct[36 + 8 * i] + bf_lo(pv[i].z), ct[37 + 8 * i] + bf_hi(pv[i].z)); pv[i].w = pack_pin(ct[38 + 8 * i] + bf_lo(pv[i].w), ct[39 + 8 * i] + bf_hi(pv[i].w));
        }
        if (tid == 0) PROF_EV(14);
        fetch(p2, 6);
        if (tid == 0) PROF_EV(24);
        check(p2, 6);
        acc4(pv, p2);
        const uint32_t stg = sb + OFF_T + warp * 2048;
        const int mr = (lane & 7) + ((lane >> 3) & 1) * 8, mc = lane >> 4;
#pragma unroll
        for (int i = 0; i < 4; i++)
          asm volatile("stmatrix.sync.aligned.m8n8.x4.shared.b16 [%0], {%1,%2,%3,%4};" ::"r"(stg + mr * 128 + (((2 * i + mc) ^ (mr & 7)) << 4)), "r"(pv[i].x),
                       "r"(pv[i].y), "r"(pv[i].z), "r"(pv[i].w) : "memory");
        asm volatile("fence.proxy.async.shared::cta;" ::: "memory");
        __syncwarp();
        if (elect_one()) {
          asm volatile("cp.async.bulk.tensor.3d.global.shared::cta.bulk_group [%0, {%2, %3, %4}], [%1];" ::"l"(&maps.o), "r"(stg), "r"(64 * j),
                       "r"(16 * w), "r"(2 * rb + wg) : "memory");
          asm volatile("cp.async.bulk.commit_group;\ncp.async.bulk.wait_group.read 0;" ::: "memory");
        }
      }
      if (tid == 0) { PROF_EV(15); PROF_CK(41); }
      if (tid == 128) PROF_EV(30);
    }
  } else if (warp < 12) {
    asm volatile("setmaxnreg.dec.sync.aligned.u32 104;");
    asm volatile("barrier.cluster.arrive.relaxed.aligned;" ::: "memory");
    const int t = tid - 256, w = warp - 8;
    const uint32_t ep = ld_x1(&ws->epoch[blockIdx.x * 8]);
    const uint32_t tag = (ep + 1) & 1;
    auto w_issue = [&](const CUtensorMap* m) {

      if (elect_one()) { mbar_expect_tx(bars + 8 * (B_WR + w), 3072); tma4d(sb + OFF_T + w * 3072, m, bars + 8 * (B_WR + w), 16 * kg, 0, 2 * w, tn); }

          __syncwarp();
    };
    auto gate_rows = [&] {
      const int r = 16 * j + 4 * w + (lane >> 3);
      const uint4* pg = (const uint4*)gate_w + (lane & 7);
      {
        float a = 0.f;
        asm volatile("bar.sync 4, 256;" ::: "memory");
#pragma unroll 1
        for (int hf = 0; hf < 2; hf++) {
          uint4 v[4], u[4];
#pragma unroll
          for (int kb = 0; kb < 4; kb++) v[kb] = __ldg(pg + (4 * hf + kb) * 8);
          mbar_wait(bars + 8 * (B_FE + 1 + 2 * hf), 0);
          if (hf) w_issue(&maps.wr);
#pragma unroll
          for (int kb = 0; kb < 4; kb++) u[kb] = *(const uint4*)(smem + (4 * hf + kb) * U + r * 128 + (((lane ^ r) & 7) << 4));
#pragma unroll
          for (int kb = 0; kb < 4; kb++) {
            const uint32_t uu[4] = {u[kb].x, u[kb].y, u[kb].z, u[kb].w}, vv[4] = {v[kb].x, v[kb].y, v[kb].z, v[kb].w};
#pragma unroll
            for (int e = 0; e < 4; e++) {
              uint32_t pr;
              asm("mul.rn.bf16x2 %0, %1, %2;" : "=r"(pr) : "r"(uu[e]), "r"(vv[e]));
              a += bf_lo(pr) + bf_hi(pr);
            }
          }
        }
#pragma unroll
        for (int o = 4; o; o >>= 1) a += __shfl_xor_sync(0xffffffffu, a, o);
        if ((lane & 7) == 0)
          asm volatile("st.relaxed.gpu.global.u32 [%0], %1;" ::"l"(ws->gate + rb * 128 + r),
                       "r"(pack_bf16(0.f, __fdividef(1.0f, 1.0f + __expf(-bf_lo(pack_bf16(a, 0.f))))) | tag) : "memory");
        if (t == 0) PROF_EV(18);
      }
    };
    {
      const int g = lane >> 2, q = lane & 3;
      uint32_t wf[32];
      if (!helper) {
        gate_rows();
        const uint32_t wa = sb + OFF_T + w * (3072 + 4) + q * 48 + g * 2;
#pragma unroll 1
        for (int ri = 0; ri < 2; ri++) {
          mbar_wait(bars + 8 * (B_WR + w), ri);
#pragma unroll
          for (int n2 = 0; n2 < 32 / WB; n2++) {
            uint32_t v[WB];
#pragma unroll
            for (int i = 0; i < WB; i++) {
              const int e = n2 * WB + i;
              asm volatile("ld.shared.u16 %0, [%1];" : "=r"(v[i]) : "r"(wa + ((e >> 1) & 7) * 192 + (e & 1) * (1536 + 2) + (e >> 4) * 16) : "memory");
            }
#pragma unroll
            for (int i = 0; i < WB; i++) wf[n2 * WB + i] = __byte_perm(wf[n2 * WB + i], v[i], 0x5432);
            if (WSLEEP) { asm volatile("nanosleep.u32 %0;" ::"r"(WSLEEP + (v[WB - 1] >> 16)) : "memory"); }
          }
          __syncwarp();
          if (ri == 0) w_issue(&maps.wi);
        }
        asm volatile("bar.sync 1, 128;" ::: "memory");
        if (t == 0) PROF_EV(11);
      } else {
        asm volatile("bar.sync 4, 256;" ::: "memory");
        hint_wait(&ws->cntW[0], (ep + 1) * 128u);
        const uint32_t t0 = (uint32_t)clock();
#pragma unroll 1
        for (;;) {
          uint32_t bad = 0;
#pragma unroll
          for (int i = 0; i < 32; i++) {
            const float2 v = ld_x2((const float2*)ws->Wh + (i >> 4) * 2048 + 16 * w + g + 8 * (i & 1) + 64 * q + ((i >> 1) & 7) * 256);
            wf[i] = __float_as_uint(v.x); bad |= __float_as_uint(v.y) ^ tag;
          }
          if (!__any_sync(0xffffffffu, bad & 1)) break;
          spin_guard(t0);
        }
        if (t == 0) PROF_EV(11);
      }
      if (w == 0 && elect_one()) { mbar_expect_tx(bars + 8 * B_W, 8192); bulk_load(sb + OFF_D, dtab, 8192, bars + 8 * B_W); }
      asm volatile("barrier.cluster.wait.aligned;" ::: "memory");
      mbar_wait(bars + 8 * B_W, 0);
      mbar_wait(bars + 8 * B_HX, 0);
      if (t == 0) PROF_EV(12);
      const uint32_t dd = (sb & 0x3FFFF) >> 4;
      const uint64_t dF = d128((dd + (OFF_D >> 4)) | (512u << 16)), dI = d128((dd + (OFF_D >> 4)) | (1u << 16)), dA = d128((dd + (OFF_XB >> 4)) | (512u << 16));
      float az[32];
      const int zero = blockIdx.x >> 16;
      uint32_t pf[32];
#pragma unroll
      for (int mt = 0; mt < 2; mt++) {
        wg_fence();
        if (mt == 0) mma_ss64<0, 3, 0>(az, dA, dF);
        else mma_ss64<0, 3, 2>(az, dA + 512, dF, zero);
#pragma unroll
        for (int k = 1; k < 4; k++) mma_ss64<0, 3, 1>(az, dA + (mt * 512 + k * 128), dF + k * 128);
        wg_commit();
        wg_wait<0>();
        fence_regs<0, 32>(az);
#pragma unroll
        for (int i = 0; i < 16; i++) {
          const float wr = bf_lo(wf[16 * mt + i]), wi = bf_hi(wf[16 * mt + i]);
          pf[16 * mt + i] = pack_pin(fmaf(az[2 * i], wr, -az[2 * i + 1] * wi), fmaf(az[2 * i], wi, az[2 * i + 1] * wr));
        }
      }
      if (t == 0) PROF_EV(16);
      {
        const int m = lane >> 3, r = lane & 7;
        const int sl = 2 * (m >> 1) + ((r >> 1) & 1) + 4 * (r >> 2);
        const uint32_t a0 = sb + OFF_XB + (2 * w + (m & 1)) * 2048 + sl * 64;
        uint32_t pk[16];
#pragma unroll
        for (int mt = 0; mt < 3; mt++) {
          if (mt < 2) {
            wg_fence();
            mma_rs64<0, 0, 2>(az, pf[16 * mt], pf[16 * mt + 1], pf[16 * mt + 2], pf[16 * mt + 3], dI, mt ? (int)helper : zero);
#pragma unroll
            for (int k = 1; k < 4; k++) mma_rs64<0, 0, 1>(az, pf[16 * mt + 4 * k], pf[16 * mt + 4 * k + 1], pf[16 * mt + 4 * k + 2], pf[16 * mt + 4 * k + 3], dI + k * 2);
            wg_commit();
          }
          if (mt > 0 && !helper) {
#pragma unroll
            for (int i = 0; i < 4; i++) stsm4t(a0 + ((((mt - 1) * 2 + (r & 1)) ^ (sl >> 1)) << 4) + i * 512, pk[4 * i], pk[4 * i + 1], pk[4 * i + 2], pk[4 * i + 3]);
          }
          if (mt < 2) {
            wg_wait<0>();
            fence_regs<0, 32>(az);
#pragma unroll
            for (int i = 0; i < 16; i++) pk[i] = pack_pin(az[2 * i], az[2 * i + 1]);
          }
        }
      }
      if (helper) {
#pragma unroll
        for (int i = 0; i < 16; i++) {
          const int n = i >> 1, s0 = 8 * (n >> 1) + 2 * (n & 1) + (q & 1) + 4 * (q >> 1);
          if ((n & 1) == (int)(blockIdx.x & 1)) st_u2(ws->Ts + s0 * 64 + 16 * w + g + 8 * (i & 1), pack_bf16(az[2 * i], az[2 * i + 1]), tag);
        }
        __syncwarp();
        hint_add_if(lane == 0, &ws->cntH[0]);
        if (t == 0) { ws->epoch[blockIdx.x * 8] = ep + 1; PROF_EV(13); }
      } else {
        asm volatile("fence.proxy.async.shared::cta;" ::: "memory");
        __syncwarp();
        if (elect_one()) {
          if (t == 0) PROF_EV(17);
          if (SPACE) __nanosleep(SPACE * w);
          asm volatile("cp.async.bulk.tensor.3d.global.shared::cta.bulk_group [%0, {%2, %3, %4}], [%1];" ::"l"(&maps.ts), "r"(sb + OFF_XB + w * 4096),
                       "r"(32 * kg), "r"(0), "r"(8 * tn + 2 * w) : "memory");
          bulk_done_signal(&ws->cntT[32 * j]);
          asm volatile("mbarrier.arrive.shared::cluster.b64 _, [%0];" ::"r"(mapa(bars + 8 * B_RD0, rank ^ 1)) : "memory");
          if (t == 96) PROF_EV(13);
        }
        __syncwarp();
        if (j == 0) {
          hint_wait(&ws->cntH[0], (ep + 1) * 8u);
          const uint32_t t0 = (uint32_t)clock();
          float2 v;
          do { v = ld_x2((const float2*)ws->Ts + 2 * rb * 64 + t); spin_guard(t0); } while (__any_sync(0xffffffffu, (__float_as_uint(v.y) ^ tag) & 1));
          mbar_wait(bars + 8 * B_TL, 0);
          const uint32_t u = __float_as_uint(v.x);
          *(uint16_t*)(smem + OFF_T + t * 128 + ((t & 7) << 4)) = (uint16_t)u;
          *(uint16_t*)(smem + OFF_T + t * 128 + (((t & 7) ^ 1) << 4)) = (uint16_t)(u >> 16);
          asm volatile("fence.proxy.async.shared::cta;" ::: "memory");
          __syncwarp();
          mbar_arrive_if(lane == 0, bars + 8 * B_T);
        }
      }
    }
  } else {
    asm volatile("setmaxnreg.dec.sync.aligned.u32 24;");
    auto xf_load = [&](int q) {
      const uint32_t fb = bars + 8 * (B_FX + q);
      mbar_expect_tx(fb, U + 8192);
      tma3d(sb + q * U, &maps.x, fb, 64 * q, 0, 2 * rb);
      if (q >= 4) mbar_wait(bars + 8 * (B_FE + ((q - 4) >> 1)), 0);
      tma2d(sb + OFF_XB + (q & 3) * 8192, &maps.ft, fb, 64 * q, 64 * j);
    };
    if (elect_one()) {
      if (warp == 14) {
#pragma unroll
        for (int i = 0; i < B_FT; i++) mbar_init(bars + 8 * i, 1);
        asm volatile("fence.mbarrier_init.release.cluster;" ::: "memory");
        if (!helper) {
#pragma unroll 1
          for (int n = 0; n < 2; n++) {
            const uint32_t fb = bars + 8 * (B_FA + n);
            xf_load(2 * n); xf_load(2 * n + 1);
            mbar_expect_tx(fb, U);
            tma2d(sb + OFF_RING + n * U, &maps.g64, fb, f_full, 64 * n);
            tma2d(sb + OFF_RING + n * U + 8192, &maps.u64, fb, f_full, 64 * n);
          }
        }
      } else if (warp == 15) {
#pragma unroll
        for (int i = B_FT; i < NBAR; i++) mbar_init(bars + 8 * i, i < B_EA ? 1 : i < B_T ? 2 : 4);
#pragma unroll
        for (int i = 0; i < 8; i++) mbar_expect_tx(bars + 8 * (B_Z + i), U / 2);
        asm volatile("fence.mbarrier_init.release.cluster;" ::: "memory");
        asm volatile("fence.proxy.async.shared::cta;" ::: "memory");
      }
    }
    __syncwarp();
    asm volatile("bar.arrive 0, 384;" ::: "memory");
    asm volatile("bar.arrive 4, 256;" ::: "memory");
    __syncwarp();
    asm volatile("barrier.cluster.arrive.relaxed.aligned;" ::: "memory");
    asm volatile("bar.sync 3, 128;" ::: "memory");
    if (warp == 15 && !helper) {
        mbar_wait(bars + 8 * B_FE, 0);
        const uint32_t tag = (ld_x1(&ws->epoch[blockIdx.x * 8]) + 1) & 1;
        const int c = lane >> 4, jj = 16 * blockIdx.x + (lane & 15), jm = (2048 - jj) & 2047;
        const unsigned short* pr = (const unsigned short*)w_r + 256 * c;
        const unsigned short* pi = (const unsigned short*)w_i + 256 * c;
        const float wr = 0.25f * (bf_lo(__ldg(pr + jj * 257)) + bf_lo(__ldg(pr + jm * 257)));
        const float wi = 0.25f * (bf_lo(__ldg(pi + jj * 257)) - bf_lo(__ldg(pi + jm * 257)));
        st_u2(ws->Wh + c * 2048 + jj, c ? pack_bf16(-wi, wr) : pack_bf16(wr, wi), tag);
        __syncwarp();
        hint_add_if(lane == 0, &ws->cntW[0]);
        mbar_wait(bars + 8 * B_XS, 0);
        const uint32_t t0 = (uint32_t)clock();
        uint4 v;
        do { v = ld_x4(ws->gate + rb * 128 + 4 * lane); spin_guard(t0); } while (__any_sync(0xffffffffu, ((v.x ^ tag) | (v.y ^ tag) | (v.z ^ tag) | (v.w ^ tag)) & 1));
        *(uint4*)(smem + OFF_G + lane * 16) = v;
        __syncwarp();
        mbar_arrive_if(lane < 4, bars + 8 * B_G);
      }
    auto part_load = [&](int i, unsigned ep1) {
      flag_wait(&ws->cntP[32 * (rb * 8 + j) + 8 * i], ep1 * 8u);
      mbar_wait(bars + 8 * (B_PZ + (i == 0)), 0);
      if (i == 2) PROF_EV(26);
      mbar_expect_tx(bars + 8 * (B_HP + i), U);
      bulk_load(sb + (i ? (i - 1) * U : OFF_T), ws->part + (size_t)((rb * 8 + j) * 3 + i) * 1024, U, bars + 8 * (B_HP + i));
    };
    if ((!helper || warp == 15) && elect_one()) {
      if (warp < 14) {
        const int p = warp - 12;
#pragma unroll 1
        for (int i = 4 + p; i < 14; i += 2) asm volatile("prefetch.tensormap [%0];" ::"l"((const char*)&maps + i * 128) : "memory");
#pragma unroll 1
        for (int n = 2; n < 31; n++) {
          const bool table = n == 4 || n >= 29;
          const bool half = n >= 17 && n < 21;
          const int q = n < 4 ? n : n < 17 ? n - 1 : n - 5;
          const CUtensorMap* m = table ? &maps.e : half ? &maps.g32 + p : &maps.g64 + p;
          const int c0 = table ? 0 : half ? f_half : f_full + 64 * (q >> 3);
          const int c1 = table ? (2 * rb + ((n & 1) ^ 1)) * 128 + 64 * p : half ? 128 * (n - 17) : 64 * (q & 7);
          const uint32_t fb = bars + 8 * (B_FA + (n & 3)), dst = sb + OFF_RING + (n & 3) * U + p * 8192;
          if (n < 4) mbar_wait(bars + 8 * (B_FE + n - 2), 0);
          else mbar_wait(bars + 8 * (B_EA + (n & 3)), ((n >> 2) & 1) ^ 1);
          tma2d(dst, m, fb, c0, c1);
          if (p == 0) mbar_expect_tx(fb, U);
        }
        mbar_wait(bars + 8 * (B_PZ + 1), 0);
        part_load(1 + p, ld_x1(&ws->epoch[blockIdx.x * 8]) + 1);
      } else if (warp == 15) {
        const unsigned ep1 = ld_x1(&ws->epoch[blockIdx.x * 8]) + 1;
        flag_wait(&ws->cntX[helper ? 0 : 32 * j], ep1 * 16u);
        PROF_EV(22);
        mbar_expect_tx(bars + 8 * B_HX, U);
        bulk_load(sb + OFF_XB, ws->X + (size_t)(helper ? 128 : kg * 8 + tn) * 8192, U, bars + 8 * B_HX);
        if (!helper) {
          flag_wait(&ws->cntT[32 * j], ep1 * 64u);
          PROF_EV(23);
          mbar_expect_tx(bars + 8 * B_TL, U);
          tma3d(sb + OFF_T, &maps.t, bars + 8 * B_TL, 64 * j, 0, 2 * rb);
          part_load(0, ep1);
          mbar_wait(bars + 8 * (B_HP + 1), 0); mbar_wait(bars + 8 * (B_HP + 2), 0);
          ws->epoch[blockIdx.x * 8] = ep1;
        }
      } else {
#pragma unroll 1
        for (int q = 4; q < 8; q++) xf_load(q);
        mbar_wait(bars + 8 * (B_FE + 2), 0);
        mbar_expect_tx(bars + 8 * B_E0, U);
        tma2d(sb + OFF_XB, &maps.e, bars + 8 * B_E0, 0, 2 * rb * 128);
        tma2d(sb + OFF_XB + 8192, &maps.e, bars + 8 * B_E0, 0, 2 * rb * 128 + 64);
#pragma unroll 1
        for (int h2 = 0; h2 < 2; h2++) {
          const int s0 = 2 * rb + h2, sg = (s0 & ~6) | ((s0 & 2) << 1) | ((s0 & 4) >> 1);
          mbar_wait(bars + 8 * (B_XS + h2), 0);
#pragma unroll 1
          for (int c = 0; c < 2; c++) {
            asm volatile("cp.async.bulk.tensor.4d.global.shared::cta.bulk_group [%0, {%2, %3, %4, %5}], [%1];" ::"l"(&maps.xs),
                         "r"(sb + OFF_XB + h2 * 8192 + c * 4096), "r"(0), "r"(sg), "r"(0), "r"(16 * j + 8 * c) : "memory");
            if (j == 0)
              asm volatile("cp.async.bulk.global.shared::cta.bulk_group [%0], [%1], 256;" ::"l"(ws->X + 128 * 8192 + c * 4096 + sg * 128),
                           "r"(sb + OFF_SP + h2 * 512 + c * 256) : "memory");
            if (SPACE && h2 + c < 2) __nanosleep(SPACE);
          }
        }
        bulk_done_signal(&ws->cntX[32 * j]);
        PROF_EV(20);
        if (rb < 8) asm volatile("cp.async.bulk.prefetch.tensor.2d.L2.global [%0, {%1, %2}];" ::"l"(&maps.g32 + (rb >> 2)), "r"(f_half), "r"(128 * (rb & 3)) : "memory");
        else asm volatile("cp.async.bulk.prefetch.tensor.2d.L2.global [%0, {%1, %2}];" ::"l"(&maps.d224), "r"(64 * (rb - 8)), "r"(224 * j) : "memory");
#pragma unroll 1
        for (int t = 0; t < 8; t++) {
          const int i = t < 3 ? t + 1 : t < 6 ? t - 2 : 0;
          const int col = 64 * (2 * ((q4 + i) & 3) + ((t < 3 || t == 6) ? 1 - rank : rank));
          const uint32_t fb = bars + 8 * (B_FT + (t & 3)), dst = sb + (t & 3) * TB;
          mbar_wait(bars + 8 * (B_ET + (t == 2 ? 3 : t & 3)), t >> 2);
          mbar_expect_tx(fb, TB);
          tma2d(dst, &maps.d224, fb, col, 224 * j);
          if (t < 2) mbar_wait(bars + 8 * (B_ET + t + 1), 0);
          tma2d(dst + 28672, &maps.ft, fb, col, 64 * j);
        }
      }
    }
  }
}

typedef CUresult (*EncodeFn)(CUtensorMap*, CUtensorMapDataType, cuuint32_t, void*, const cuuint64_t*, const cuuint64_t*, const cuuint32_t*,
                             const cuuint32_t*, CUtensorMapInterleave, CUtensorMapSwizzle, CUtensorMapL2promotion, CUtensorMapFloatOOBfill);

static void encode(EncodeFn f, CUtensorMap* m, const void* base, int rank, const cuuint64_t* dims, const cuuint64_t* strides, const cuuint32_t* box,
                   CUtensorMapSwizzle sw) {
  cuuint32_t es[5] = {1, 1, 1, 1, 1};
  f(m, CU_TENSOR_MAP_DATA_TYPE_BFLOAT16, rank, (void*)base, dims, strides, box, es, CU_TENSOR_MAP_INTERLEAVE_NONE, sw,
    CU_TENSOR_MAP_L2_PROMOTION_L2_128B, CU_TENSOR_MAP_FLOAT_OOB_FILL_NONE);
}

extern "C" void kernel_launch(void* const* d_in, const int* in_sizes, int n_in, void* d_out, int out_size) {
  (void)in_sizes; (void)n_in; (void)out_size;
  const __nv_bfloat16* x = (const __nv_bfloat16*)d_in[0];
  const __nv_bfloat16* w_r = (const __nv_bfloat16*)d_in[1];
  const __nv_bfloat16* w_i = (const __nv_bfloat16*)d_in[2];
  const __nv_bfloat16* Wg = (const __nv_bfloat16*)d_in[4];
  const __nv_bfloat16* Wu = (const __nv_bfloat16*)d_in[5];
  const __nv_bfloat16* Wd = (const __nv_bfloat16*)d_in[6];
  const __nv_bfloat16* gw = (const __nv_bfloat16*)d_in[7];

  void* fp = nullptr; cudaDriverEntryPointQueryResult qr;
  cudaGetDriverEntryPoint("cuTensorMapEncodeTiled", &fp, cudaEnableDefault, &qr);
  EncodeFn enc = (EncodeFn)fp;
  void *pFT, *pET, *pDT, *pW;
  cudaGetSymbolAddress(&pDT, g_DT); cudaGetSymbolAddress(&pW, g_work);
  void *pX = ((Work*)pW)->X, *pT = ((Work*)pW)->T;
  cudaGetSymbolAddress(&pFT, g_FT); cudaGetSymbolAddress(&pET, g_ET);

  Maps mp;
  const CUtensorMapSwizzle S128 = CU_TENSOR_MAP_SWIZZLE_128B, S64 = CU_TENSOR_MAP_SWIZZLE_64B;
  { cuuint64_t d[3] = {512, 64, 32}, s[2] = {32768, 1024}; cuuint32_t b[3] = {64, 64, 2}, b2[3] = {64, 16, 1};
    encode(enc, &mp.x, x, 3, d, s, b, S128); encode(enc, &mp.o, d_out, 3, d, s, b2, S128); }
  { cuuint64_t d[2] = {512, 512}, s[1] = {1024}; cuuint32_t b[2] = {64, 64}; encode(enc, &mp.ft, pFT, 2, d, s, b, S128); }
  { cuuint64_t d[4] = {128, 32, 2, 129}, s[3] = {256, 8192, 16384}; cuuint32_t b[4] = {128, 1, 2, 8}; encode(enc, &mp.xs, pX, 4, d, s, b, CU_TENSOR_MAP_SWIZZLE_NONE); }
  { cuuint64_t d[3] = {512, 32, 64}, s[2] = {65536, 1024}; cuuint32_t b[3] = {32, 32, 2}; encode(enc, &mp.ts, pT, 3, d, s, b, S64); }
  { cuuint64_t d[3] = {512, 64, 32}, s[2] = {1024, 65536}; cuuint32_t b[3] = {64, 64, 2}; encode(enc, &mp.t, pT, 3, d, s, b, S128); }
  { cuuint64_t d[2] = {64, 4096}, s[1] = {128}; cuuint32_t b[2] = {64, 64}; encode(enc, &mp.e, pET, 2, d, s, b, S128); }
  { cuuint64_t d[2] = {1792, 512}, s[1] = {3584}; cuuint32_t b[2] = {64, 64}, b2[2] = {32, 128};
    encode(enc, &mp.g64, Wg, 2, d, s, b, S128); encode(enc, &mp.u64, Wu, 2, d, s, b, S128);
    encode(enc, &mp.g32, Wg, 2, d, s, b2, S64); encode(enc, &mp.u32, Wu, 2, d, s, b2, S64); }
  { cuuint64_t d[2] = {512, 1792}, s[1] = {1024}; cuuint32_t b[2] = {64, 224}; encode(enc, &mp.d224, Wd, 2, d, s, b, S128); }
  { cuuint64_t d[4] = {264, 32, 8, 8}, s[3] = {32896, 512, 4112}; cuuint32_t b[4] = {24, 32, 2, 1};
    encode(enc, &mp.wr, w_r, 4, d, s, b, CU_TENSOR_MAP_SWIZZLE_NONE); encode(enc, &mp.wi, w_i, 4, d, s, b, CU_TENSOR_MAP_SWIZZLE_NONE); }

  cudaFuncSetAttribute(fused_kernel, cudaFuncAttributeMaxDynamicSharedMemorySize, SMEM_BYTES);
  fused_kernel<<<NCTA, 512, SMEM_BYTES>>>((Work*)pW, (const uint16_t*)pDT, w_r, w_i, gw, x, mp);
}
```

```cpp
#include <cuda_runtime.h>
#include <cuda_bf16.h>
#include <cuda.h>
#include <stdint.h>

namespace tbl {
constexpr double PI = 3.14159265358979323846264338327950288;
constexpr double sin_s(double x) { double t = x, s = x; for (int n = 1; n < 12; n++) { t *= -x * x / ((2 * n) * (2 * n + 1)); s += t; } return s; }
constexpr double cos_s(double x) { double t = 1, s = 1; for (int n = 1; n < 12; n++) { t *= -x * x / ((2 * n - 1) * (2 * n)); s += t; } return s; }
constexpr double cos2048(int m) {
  m &= 2047; if (m > 1024) m = 2048 - m;
  bool neg = false; if (m > 512) { m = 1024 - m; neg = true; }
  double v = (m <= 256) ? cos_s(2 * PI * m / 2048) : sin_s(2 * PI * (512 - m) / 2048);
  return neg ? -v : v;
}
constexpr uint16_t to_bf16(double v) {
  if (v == 0) return 0;
  uint16_t s = 0; if (v < 0) { s = 0x8000; v = -v; }
  int e = 0; while (v >= 2) { v /= 2; e++; } while (v < 1) { v *= 2; e--; }
  double m = (v - 1) * 128; int mi = (int)m; double fr = m - mi;
  if (fr > 0.5 || (fr == 0.5 && (mi & 1))) mi++;
  if (mi == 128) { mi = 0; e++; }
  return (uint16_t)(s | ((e + 127) << 7) | mi);
}
struct CosT { uint16_t v[2048]; constexpr CosT() : v() { for (int i = 0; i < 2048; i++) v[i] = to_bf16(cos2048(i)); } };
struct alignas(1024) FT {
  uint16_t v[512 * 512];
  constexpr FT() : v() {
    CosT c;
    for (int r = 0; r < 512; r++) {
      int k = (r >> 4) * 8 + (r & 7), e = (r >> 3) & 1;
      int mul = 4 * k, add = e ? 512 : 0;
      if (k == 0 && e == 1) { mul = 1024; add = 0; }
      for (int d = 0; d < 512; d++) v[r * 512 + d] = c.v[(d * mul + add) & 2047];
    }
  }
};
struct alignas(1024) ET {
  uint16_t v[2048 * 128];
  constexpr ET() : v() {
    CosT c;
    for (int s = 0; s < 2048; s++)
      for (int j = 0; j < 64; j++) {
        const int o = (s & 31) * 8192 + (s >> 5) * 64 + j;
        v[o] = c.v[(s * j) & 2047]; v[o + 4096] = c.v[(s * j + 512) & 2047];
      }
  }
};
struct alignas(1024) DT {
  uint16_t v[64 * 64];
  constexpr DT() : v() {
    CosT c;
    for (int r = 0; r < 64; r++)
      for (int n = 0; n < 64; n++) {
        const int sg = r >> 1, s0 = (sg & ~6) | ((sg & 2) << 1) | ((sg & 4) >> 1), e = r & 1, f = n & 1;
        const int m = 64 * s0 * (n >> 1) + (e == f ? 0 : e ? -512 : 512);
        v[r * 64 + (((n >> 3) ^ (r & 7)) << 3) + (n & 7)] = c.v[m & 2047];
      }
  }
};
}

__device__ constexpr tbl::FT g_FT = tbl::FT();
__device__ constexpr tbl::ET g_ET = tbl::ET();
__device__ constexpr tbl::DT g_DT = tbl::DT();

struct alignas(1024) Work {
  unsigned epoch[132 * 8];
  unsigned cntX[8 * 32], cntT[8 * 32], cntP[128 * 32], cntW[32], cntH[32];
  alignas(16) float gate[16 * 128];
  alignas(16) uint2 Wh[2 * 2048];
  alignas(16) uint2 Ts[32 * 64];
  alignas(1024) uint16_t X[129 * 8192];
  alignas(1024) uint16_t T[32 * 64 * 512];
  alignas(1024) uint4 part[128 * 3 * 1024];
};
__device__ Work g_work;
#define PROF_EV(i) do {} while (0)
#define PROF_CK(i) do {} while (0)

__device__ __forceinline__ uint32_t smem_u32(const void* p) { return (uint32_t)__cvta_generic_to_shared(p); }
__device__ __forceinline__ void mbar_init(uint32_t bar, uint32_t cnt) { asm volatile("mbarrier.init.shared::cta.b64 [%0], %1;" ::"r"(bar), "r"(cnt)); }
__device__ __forceinline__ void mbar_expect_tx(uint32_t bar, uint32_t bytes) { asm volatile("mbarrier.arrive.expect_tx.shared::cta.b64 _, [%0], %1;" ::"r"(bar), "r"(bytes) : "memory"); }
__device__ __forceinline__ void mbar_arrive(uint32_t bar) { asm volatile("mbarrier.arrive.shared::cta.b64 _, [%0];" ::"r"(bar) : "memory"); }
__device__ __forceinline__ bool elect_one() {
  uint32_t p;
  asm volatile("{\n.reg .pred p;\nelect.sync _|p, 0xffffffff;\nselp.u32 %0, 1, 0, p;\n}" : "=r"(p));
  return p;
}
__device__ __forceinline__ void mbar_arrive_if(bool p, uint32_t bar) {
  asm volatile("{\n.reg .pred p;\nsetp.ne.b32 p, %1, 0;\n@p mbarrier.arrive.shared::cta.b64 _, [%0];\n}" ::"r"(bar), "r"((int)p) : "memory");
}
__device__ __forceinline__ void hint_add_if(bool p, unsigned* a) {
  asm volatile("{\n.reg .pred p;\nsetp.ne.b32 p, %1, 0;\n@p red.relaxed.gpu.global.add.u32 [%0], 1;\n}" ::"l"(a), "r"((int)p) : "memory");
}
__device__ __forceinline__ bool mbar_try(uint32_t bar, uint32_t parity) {
  uint32_t ok;
  asm volatile("{\n.reg .pred p;\nmbarrier.test_wait.parity.shared::cta.b64 p, [%1], %2;\nselp.u32 %0, 1, 0, p;\n}" : "=r"(ok) : "r"(bar), "r"(parity) : "memory");
  return ok;
}
__device__ __forceinline__ void mbar_wait(uint32_t bar, uint32_t parity) {
  asm volatile(
      "{\n.reg .pred p;\n.reg .u32 n;\nmov.u32 n, 0;\n"
      "W_LOOP:\nmbarrier.try_wait.parity.shared::cta.b64 p, [%0], %1;\n@p bra W_DONE;\n"
      "add.u32 n, n, 1;\nsetp.lt.u32 p, n, 0x40000;\n@p bra W_LOOP;\ntrap;\nW_DONE:\n}" ::"r"(bar), "r"(parity) : "memory");
}
__device__ __forceinline__ void bulk_load(uint32_t dst, const void* src, uint32_t bytes, uint32_t bar) {
  asm volatile("cp.async.bulk.shared::cluster.global.mbarrier::complete_tx::bytes [%0], [%1], %2, [%3];" ::"r"(dst), "l"(src), "r"(bytes), "r"(bar) : "memory");
}
__device__ __forceinline__ void spin_guard(uint32_t t0) { if ((uint32_t)clock() - t0 > (1u << 30)) __trap(); }
__device__ __forceinline__ float2 ld_x2(const float2* p) { float2 v; asm volatile("ld.relaxed.gpu.global.v2.f32 {%0,%1}, [%2];" : "=f"(v.x), "=f"(v.y) : "l"(p) : "memory"); return v; }
__device__ __forceinline__ void st_u2(uint2* p, uint32_t a, uint32_t b) { asm volatile("st.relaxed.gpu.global.v2.u32 [%0], {%1,%2};" ::"l"(p), "r"(a), "r"(b) : "memory"); }
__device__ __forceinline__ uint32_t ld_x1(const void* p) { uint32_t v; asm volatile("ld.relaxed.gpu.global.u32 %0, [%1];" : "=r"(v) : "l"(p) : "memory"); return v; }
__device__ __forceinline__ uint4 ld_x4(const void* p) { uint4 v; asm volatile("ld.relaxed.gpu.global.v4.u32 {%0,%1,%2,%3}, [%4];" : "=r"(v.x), "=r"(v.y), "=r"(v.z), "=r"(v.w) : "l"(p) : "memory"); return v; }
__device__ __forceinline__ uint32_t mapa(uint32_t a, uint32_t cta) { uint32_t r; asm volatile("mapa.shared::cluster.u32 %0, %1, %2;" : "=r"(r) : "r"(a), "r"(cta)); return r; }
__device__ __forceinline__ void stsm4t(uint32_t a, uint32_t r0, uint32_t r1, uint32_t r2, uint32_t r3) {
  asm volatile("stmatrix.sync.aligned.m8n8.x4.trans.shared.b16 [%0], {%1,%2,%3,%4};" ::"r"(a), "r"(r0), "r"(r1), "r"(r2), "r"(r3) : "memory");
}
__device__ __forceinline__ void hint_add(unsigned* p) { asm volatile("red.relaxed.gpu.global.add.u32 [%0], 1;" ::"l"(p) : "memory"); }
__device__ __forceinline__ void hint_wait(const unsigned* p, unsigned target) {
  const uint32_t t0 = (uint32_t)clock();
  while ((int)(ld_x1(p) - target) < 0) spin_guard(t0);
}
__device__ __forceinline__ void bulk_done_signal(unsigned* p) {
  asm volatile("cp.async.bulk.commit_group;\ncp.async.bulk.wait_group 0;\nfence.proxy.async.global;" ::: "memory");
  hint_add(p);
}
__device__ __forceinline__ void flag_wait(const unsigned* p, unsigned target) {
  hint_wait(p, target);
  asm volatile("fence.proxy.async.global;" ::: "memory");
}
__device__ __forceinline__ void tma2d(uint32_t dst, const CUtensorMap* m, uint32_t bar, int c0, int c1) {
  asm volatile("cp.async.bulk.tensor.2d.shared::cluster.global.mbarrier::complete_tx::bytes [%0], [%1, {%3, %4}], [%2];" ::"r"(dst), "l"(m), "r"(bar), "r"(c0), "r"(c1) : "memory");
}
__device__ __forceinline__ void tma3d(uint32_t dst, const CUtensorMap* m, uint32_t bar, int c0, int c1, int c2) {
  asm volatile("cp.async.bulk.tensor.3d.shared::cluster.global.mbarrier::complete_tx::bytes [%0], [%1, {%3, %4, %5}], [%2];" ::"r"(dst), "l"(m), "r"(bar), "r"(c0), "r"(c1), "r"(c2) : "memory");
}
__device__ __forceinline__ void tma4d(uint32_t dst, const CUtensorMap* m, uint32_t bar, int c0, int c1, int c2, int c3) {
  asm volatile("cp.async.bulk.tensor.4d.shared::cluster.global.mbarrier::complete_tx::bytes [%0], [%1, {%3, %4, %5, %6}], [%2];" ::"r"(dst), "l"(m), "r"(bar), "r"(c0), "r"(c1), "r"(c2), "r"(c3) : "memory");
}
__device__ __forceinline__ void wg_fence() { asm volatile("wgmma.fence.sync.aligned;" ::: "memory"); }
__device__ __forceinline__ void wg_commit() { asm volatile("wgmma.commit_group.sync.aligned;" ::: "memory"); }
template <int N> __device__ __forceinline__ void wg_wait() { asm volatile("wgmma.wait_group.sync.aligned %0;" ::"n"(N) : "memory"); }
template <int O, int N, int NN> __device__ __forceinline__ void fence_regs(float (&d)[NN]) {
#pragma unroll
  for (int i = 0; i < N; i++) asm volatile("" : "+f"(d[O + i])::"memory");
}
__device__ __forceinline__ uint32_t pack_bf16(float lo, float hi) {
  uint32_t r; asm("cvt.rn.bf16x2.f32 %0, %1, %2;" : "=r"(r) : "f"(hi), "f"(lo)); return r;
}
__device__ __forceinline__ uint32_t pack_pin(float lo, float hi) {
  uint32_t r; asm volatile("cvt.rn.bf16x2.f32 %0, %1, %2;" : "=r"(r) : "f"(hi), "f"(lo) : "memory"); return r;
}
__device__ __forceinline__ uint32_t add_bf2(uint32_t a, uint32_t b) { uint32_t r; asm("add.rn.bf16x2 %0, %1, %2;" : "=r"(r) : "r"(a), "r"(b)); return r; }
__device__ __forceinline__ float bf_lo(uint32_t u) { return __uint_as_float(u << 16); }
__device__ __forceinline__ float bf_hi(uint32_t u) { return __uint_as_float(u & 0xffff0000u); }

__device__ __forceinline__ uint64_t d128(uint32_t lo) { uint64_t d; asm("mov.b64 %0, {%1, 0x40000040};" : "=l"(d) : "r"(lo)); return d; }
__device__ __forceinline__ uint64_t d64(uint32_t lo) { uint64_t d; asm("mov.b64 %0, {%1, 0x80000020};" : "=l"(d) : "r"(lo)); return d; }
template<int O,int TB,int ACC,int NN> __device__ __forceinline__ void mma_ss64(float (&d)[NN], uint64_t da, uint64_t db, int sd = 0){
  if constexpr (ACC == 1) asm volatile("wgmma.mma_async.sync.aligned.m64n64k16.f32.bf16.bf16 {%0,%1,%2,%3,%4,%5,%6,%7,%8,%9,%10,%11,%12,%13,%14,%15,%16,%17,%18,%19,%20,%21,%22,%23,%24,%25,%26,%27,%28,%29,%30,%31}, %32, %33, 1, 1, 1, %35, %34;"
   : "+f"(d[O+0]), "+f"(d[O+1]), "+f"(d[O+2]), "+f"(d[O+3]), "+f"(d[O+4]), "+f"(d[O+5]), "+f"(d[O+6]), "+f"(d[O+7]), "+f"(d[O+8]), "+f"(d[O+9]), "+f"(d[O+10]), "+f"(d[O+11]), "+f"(d[O+12]), "+f"(d[O+13]), "+f"(d[O+14]), "+f"(d[O+15]), "+f"(d[O+16]), "+f"(d[O+17]), "+f"(d[O+18]), "+f"(d[O+19]), "+f"(d[O+20]), "+f"(d[O+21]), "+f"(d[O+22]), "+f"(d[O+23]), "+f"(d[O+24]), "+f"(d[O+25]), "+f"(d[O+26]), "+f"(d[O+27]), "+f"(d[O+28]), "+f"(d[O+29]), "+f"(d[O+30]), "+f"(d[O+31])
   : "l"(da), "l"(db), "n"(TB & 1), "n"(TB >> 1));
  else if constexpr (ACC == 0) asm volatile("wgmma.mma_async.sync.aligned.m64n64k16.f32.bf16.bf16 {%0,%1,%2,%3,%4,%5,%6,%7,%8,%9,%10,%11,%12,%13,%14,%15,%16,%17,%18,%19,%20,%21,%22,%23,%24,%25,%26,%27,%28,%29,%30,%31}, %32, %33, 0, 1, 1, %35, %34;"
   : "=f"(d[O+0]), "=f"(d[O+1]), "=f"(d[O+2]), "=f"(d[O+3]), "=f"(d[O+4]), "=f"(d[O+5]), "=f"(d[O+6]), "=f"(d[O+7]), "=f"(d[O+8]), "=f"(d[O+9]), "=f"(d[O+10]), "=f"(d[O+11]), "=f"(d[O+12]), "=f"(d[O+13]), "=f"(d[O+14]), "=f"(d[O+15]), "=f"(d[O+16]), "=f"(d[O+17]), "=f"(d[O+18]), "=f"(d[O+19]), "=f"(d[O+20]), "=f"(d[O+21]), "=f"(d[O+22]), "=f"(d[O+23]), "=f"(d[O+24]), "=f"(d[O+25]), "=f"(d[O+26]), "=f"(d[O+27]), "=f"(d[O+28]), "=f"(d[O+29]), "=f"(d[O+30]), "=f"(d[O+31])
   : "l"(da), "l"(db), "n"(TB & 1), "n"(TB >> 1));
  else asm volatile("{\n.reg .pred p;\nsetp.ne.b32 p, %36, 0;\nwgmma.mma_async.sync.aligned.m64n64k16.f32.bf16.bf16 {%0,%1,%2,%3,%4,%5,%6,%7,%8,%9,%10,%11,%12,%13,%14,%15,%16,%17,%18,%19,%20,%21,%22,%23,%24,%25,%26,%27,%28,%29,%30,%31}, %32, %33, p, 1, 1, %35, %34;\n}"
   : "+f"(d[O+0]), "+f"(d[O+1]), "+f"(d[O+2]), "+f"(d[O+3]), "+f"(d[O+4]), "+f"(d[O+5]), "+f"(d[O+6]), "+f"(d[O+7]), "+f"(d[O+8]), "+f"(d[O+9]), "+f"(d[O+10]), "+f"(d[O+11]), "+f"(d[O+12]), "+f"(d[O+13]), "+f"(d[O+14]), "+f"(d[O+15]), "+f"(d[O+16]), "+f"(d[O+17]), "+f"(d[O+18]), "+f"(d[O+19]), "+f"(d[O+20]), "+f"(d[O+21]), "+f"(d[O+22]), "+f"(d[O+23]), "+f"(d[O+24]), "+f"(d[O+25]), "+f"(d[O+26]), "+f"(d[O+27]), "+f"(d[O+28]), "+f"(d[O+29]), "+f"(d[O+30]), "+f"(d[O+31])
   : "l"(da), "l"(db), "n"(TB & 1), "n"(TB >> 1), "r"(sd));
}
template<int O,int TB,int ACC,int NN> __device__ __forceinline__ void mma_rs64(float (&d)[NN], uint32_t a0, uint32_t a1, uint32_t a2, uint32_t a3, uint64_t db, int sd = 0){
  if constexpr (ACC == 1) asm volatile("wgmma.mma_async.sync.aligned.m64n64k16.f32.bf16.bf16 {%0,%1,%2,%3,%4,%5,%6,%7,%8,%9,%10,%11,%12,%13,%14,%15,%16,%17,%18,%19,%20,%21,%22,%23,%24,%25,%26,%27,%28,%29,%30,%31}, {%32,%33,%34,%35}, %36, 1, 1, 1, %37;"
   : "+f"(d[O+0]), "+f"(d[O+1]), "+f"(d[O+2]), "+f"(d[O+3]), "+f"(d[O+4]), "+f"(d[O+5]), "+f"(d[O+6]), "+f"(d[O+7]), "+f"(d[O+8]), "+f"(d[O+9]), "+f"(d[O+10]), "+f"(d[O+11]), "+f"(d[O+12]), "+f"(d[O+13]), "+f"(d[O+14]), "+f"(d[O+15]), "+f"(d[O+16]), "+f"(d[O+17]), "+f"(d[O+18]), "+f"(d[O+19]), "+f"(d[O+20]), "+f"(d[O+21]), "+f"(d[O+22]), "+f"(d[O+23]), "+f"(d[O+24]), "+f"(d[O+25]), "+f"(d[O+26]), "+f"(d[O+27]), "+f"(d[O+28]), "+f"(d[O+29]), "+f"(d[O+30]), "+f"(d[O+31])
   : "r"(a0), "r"(a1), "r"(a2), "r"(a3), "l"(db), "n"(TB));
  else if constexpr (ACC == 0) asm volatile("wgmma.mma_async.sync.aligned.m64n64k16.f32.bf16.bf16 {%0,%1,%2,%3,%4,%5,%6,%7,%8,%9,%10,%11,%12,%13,%14,%15,%16,%17,%18,%19,%20,%21,%22,%23,%24,%25,%26,%27,%28,%29,%30,%31}, {%32,%33,%34,%35}, %36, 0, 1, 1, %37;"
   : "=f"(d[O+0]), "=f"(d[O+1]), "=f"(d[O+2]), "=f"(d[O+3]), "=f"(d[O+4]), "=f"(d[O+5]), "=f"(d[O+6]), "=f"(d[O+7]), "=f"(d[O+8]), "=f"(d[O+9]), "=f"(d[O+10]), "=f"(d[O+11]), "=f"(d[O+12]), "=f"(d[O+13]), "=f"(d[O+14]), "=f"(d[O+15]), "=f"(d[O+16]), "=f"(d[O+17]), "=f"(d[O+18]), "=f"(d[O+19]), "=f"(d[O+20]), "=f"(d[O+21]), "=f"(d[O+22]), "=f"(d[O+23]), "=f"(d[O+24]), "=f"(d[O+25]), "=f"(d[O+26]), "=f"(d[O+27]), "=f"(d[O+28]), "=f"(d[O+29]), "=f"(d[O+30]), "=f"(d[O+31])
   : "r"(a0), "r"(a1), "r"(a2), "r"(a3), "l"(db), "n"(TB));
  else asm volatile("{\n.reg .pred p;\nsetp.ne.b32 p, %38, 0;\nwgmma.mma_async.sync.aligned.m64n64k16.f32.bf16.bf16 {%0,%1,%2,%3,%4,%5,%6,%7,%8,%9,%10,%11,%12,%13,%14,%15,%16,%17,%18,%19,%20,%21,%22,%23,%24,%25,%26,%27,%28,%29,%30,%31}, {%32,%33,%34,%35}, %36, p, 1, 1, %37;\n}"
   : "+f"(d[O+0]), "+f"(d[O+1]), "+f"(d[O+2]), "+f"(d[O+3]), "+f"(d[O+4]), "+f"(d[O+5]), "+f"(d[O+6]), "+f"(d[O+7]), "+f"(d[O+8]), "+f"(d[O+9]), "+f"(d[O+10]), "+f"(d[O+11]), "+f"(d[O+12]), "+f"(d[O+13]), "+f"(d[O+14]), "+f"(d[O+15]), "+f"(d[O+16]), "+f"(d[O+17]), "+f"(d[O+18]), "+f"(d[O+19]), "+f"(d[O+20]), "+f"(d[O+21]), "+f"(d[O+22]), "+f"(d[O+23]), "+f"(d[O+24]), "+f"(d[O+25]), "+f"(d[O+26]), "+f"(d[O+27]), "+f"(d[O+28]), "+f"(d[O+29]), "+f"(d[O+30]), "+f"(d[O+31])
   : "r"(a0), "r"(a1), "r"(a2), "r"(a3), "l"(db), "n"(TB), "r"(sd));
}
template<int O,int TB,int ACC,int NN> __device__ __forceinline__ void mma_ss128(float (&d)[NN], uint64_t da, uint64_t db, int sd = 0){
  if constexpr (ACC == 1) asm volatile("wgmma.mma_async.sync.aligned.m64n128k16.f32.bf16.bf16 {%0,%1,%2,%3,%4,%5,%6,%7,%8,%9,%10,%11,%12,%13,%14,%15,%16,%17,%18,%19,%20,%21,%22,%23,%24,%25,%26,%27,%28,%29,%30,%31,%32,%33,%34,%35,%36,%37,%38,%39,%40,%41,%42,%43,%44,%45,%46,%47,%48,%49,%50,%51,%52,%53,%54,%55,%56,%57,%58,%59,%60,%61,%62,%63}, %64, %65, 1, 1, 1, %67, %66;"
   : "+f"(d[O+0]), "+f"(d[O+1]), "+f"(d[O+2]), "+f"(d[O+3]), "+f"(d[O+4]), "+f"(d[O+5]), "+f"(d[O+6]), "+f"(d[O+7]), "+f"(d[O+8]), "+f"(d[O+9]), "+f"(d[O+10]), "+f"(d[O+11]), "+f"(d[O+12]), "+f"(d[O+13]), "+f"(d[O+14]), "+f"(d[O+15]), "+f"(d[O+16]), "+f"(d[O+17]), "+f"(d[O+18]), "+f"(d[O+19]), "+f"(d[O+20]), "+f"(d[O+21]), "+f"(d[O+22]), "+f"(d[O+23]), "+f"(d[O+24]), "+f"(d[O+25]), "+f"(d[O+26]), "+f"(d[O+27]), "+f"(d[O+28]), "+f"(d[O+29]), "+f"(d[O+30]), "+f"(d[O+31]), "+f"(d[O+32]), "+f"(d[O+33]), "+f"(d[O+34]), "+f"(d[O+35]), "+f"(d[O+36]), "+f"(d[O+37]), "+f"(d[O+38]), "+f"(d[O+39]), "+f"(d[O+40]), "+f"(d[O+41]), "+f"(d[O+42]), "+f"(d[O+43]), "+f"(d[O+44]), "+f"(d[O+45]), "+f"(d[O+46]), "+f"(d[O+47]), "+f"(d[O+48]), "+f"(d[O+49]), "+f"(d[O+50]), "+f"(d[O+51]), "+f"(d[O+52]), "+f"(d[O+53]), "+f"(d[O+54]), "+f"(d[O+55]), "+f"(d[O+56]), "+f"(d[O+57]), "+f"(d[O+58]), "+f"(d[O+59]), "+f"(d[O+60]), "+f"(d[O+61]), "+f"(d[O+62]), "+f"(d[O+63])
   : "l"(da), "l"(db), "n"(TB & 1), "n"(TB >> 1));
  else if constexpr (ACC == 0) asm volatile("wgmma.mma_async.sync.aligned.m64n128k16.f32.bf16.bf16 {%0,%1,%2,%3,%4,%5,%6,%7,%8,%9,%10,%11,%12,%13,%14,%15,%16,%17,%18,%19,%20,%21,%22,%23,%24,%25,%26,%27,%28,%29,%30,%31,%32,%33,%34,%35,%36,%37,%38,%39,%40,%41,%42,%43,%44,%45,%46,%47,%48,%49,%50,%51,%52,%53,%54,%55,%56,%57,%58,%59,%60,%61,%62,%63}, %64, %65, 0, 1, 1, %67, %66;"
   : "=f"(d[O+0]), "=f"(d[O+1]), "=f"(d[O+2]), "=f"(d[O+3]), "=f"(d[O+4]), "=f"(d[O+5]), "=f"(d[O+6]), "=f"(d[O+7]), "=f"(d[O+8]), "=f"(d[O+9]), "=f"(d[O+10]), "=f"(d[O+11]), "=f"(d[O+12]), "=f"(d[O+13]), "=f"(d[O+14]), "=f"(d[O+15]), "=f"(d[O+16]), "=f"(d[O+17]), "=f"(d[O+18]), "=f"(d[O+19]), "=f"(d[O+20]), "=f"(d[O+21]), "=f"(d[O+22]), "=f"(d[O+23]), "=f"(d[O+24]), "=f"(d[O+25]), "=f"(d[O+26]), "=f"(d[O+27]), "=f"(d[O+28]), "=f"(d[O+29]), "=f"(d[O+30]), "=f"(d[O+31]), "=f"(d[O+32]), "=f"(d[O+33]), "=f"(d[O+34]), "=f"(d[O+35]), "=f"(d[O+36]), "=f"(d[O+37]), "=f"(d[O+38]), "=f"(d[O+39]), "=f"(d[O+40]), "=f"(d[O+41]), "=f"(d[O+42]), "=f"(d[O+43]), "=f"(d[O+44]), "=f"(d[O+45]), "=f"(d[O+46]), "=f"(d[O+47]), "=f"(d[O+48]), "=f"(d[O+49]), "=f"(d[O+50]), "=f"(d[O+51]), "=f"(d[O+52]), "=f"(d[O+53]), "=f"(d[O+54]), "=f"(d[O+55]), "=f"(d[O+56]), "=f"(d[O+57]), "=f"(d[O+58]), "=f"(d[O+59]), "=f"(d[O+60]), "=f"(d[O+61]), "=f"(d[O+62]), "=f"(d[O+63])
   : "l"(da), "l"(db), "n"(TB & 1), "n"(TB >> 1));
  else asm volatile("{\n.reg .pred p;\nsetp.ne.b32 p, %68, 0;\nwgmma.mma_async.sync.aligned.m64n128k16.f32.bf16.bf16 {%0,%1,%2,%3,%4,%5,%6,%7,%8,%9,%10,%11,%12,%13,%14,%15,%16,%17,%18,%19,%20,%21,%22,%23,%24,%25,%26,%27,%28,%29,%30,%31,%32,%33,%34,%35,%36,%37,%38,%39,%40,%41,%42,%43,%44,%45,%46,%47,%48,%49,%50,%51,%52,%53,%54,%55,%56,%57,%58,%59,%60,%61,%62,%63}, %64, %65, p, 1, 1, %67, %66;\n}"
   : "+f"(d[O+0]), "+f"(d[O+1]), "+f"(d[O+2]), "+f"(d[O+3]), "+f"(d[O+4]), "+f"(d[O+5]), "+f"(d[O+6]), "+f"(d[O+7]), "+f"(d[O+8]), "+f"(d[O+9]), "+f"(d[O+10]), "+f"(d[O+11]), "+f"(d[O+12]), "+f"(d[O+13]), "+f"(d[O+14]), "+f"(d[O+15]), "+f"(d[O+16]), "+f"(d[O+17]), "+f"(d[O+18]), "+f"(d[O+19]), "+f"(d[O+20]), "+f"(d[O+21]), "+f"(d[O+22]), "+f"(d[O+23]), "+f"(d[O+24]), "+f"(d[O+25]), "+f"(d[O+26]), "+f"(d[O+27]), "+f"(d[O+28]), "+f"(d[O+29]), "+f"(d[O+30]), "+f"(d[O+31]), "+f"(d[O+32]), "+f"(d[O+33]), "+f"(d[O+34]), "+f"(d[O+35]), "+f"(d[O+36]), "+f"(d[O+37]), "+f"(d[O+38]), "+f"(d[O+39]), "+f"(d[O+40]), "+f"(d[O+41]), "+f"(d[O+42]), "+f"(d[O+43]), "+f"(d[O+44]), "+f"(d[O+45]), "+f"(d[O+46]), "+f"(d[O+47]), "+f"(d[O+48]), "+f"(d[O+49]), "+f"(d[O+50]), "+f"(d[O+51]), "+f"(d[O+52]), "+f"(d[O+53]), "+f"(d[O+54]), "+f"(d[O+55]), "+f"(d[O+56]), "+f"(d[O+57]), "+f"(d[O+58]), "+f"(d[O+59]), "+f"(d[O+60]), "+f"(d[O+61]), "+f"(d[O+62]), "+f"(d[O+63])
   : "l"(da), "l"(db), "n"(TB & 1), "n"(TB >> 1), "r"(sd));
}
template<int O,int TB,int ACC,int NN> __device__ __forceinline__ void mma_rs128(float (&d)[NN], uint32_t a0, uint32_t a1, uint32_t a2, uint32_t a3, uint64_t db, int sd = 0){
  if constexpr (ACC == 1) asm volatile("wgmma.mma_async.sync.aligned.m64n128k16.f32.bf16.bf16 {%0,%1,%2,%3,%4,%5,%6,%7,%8,%9,%10,%11,%12,%13,%14,%15,%16,%17,%18,%19,%20,%21,%22,%23,%24,%25,%26,%27,%28,%29,%30,%31,%32,%33,%34,%35,%36,%37,%38,%39,%40,%41,%42,%43,%44,%45,%46,%47,%48,%49,%50,%51,%52,%53,%54,%55,%56,%57,%58,%59,%60,%61,%62,%63}, {%64,%65,%66,%67}, %68, 1, 1, 1, %69;"
   : "+f"(d[O+0]), "+f"(d[O+1]), "+f"(d[O+2]), "+f"(d[O+3]), "+f"(d[O+4]), "+f"(d[O+5]), "+f"(d[O+6]), "+f"(d[O+7]), "+f"(d[O+8]), "+f"(d[O+9]), "+f"(d[O+10]), "+f"(d[O+11]), "+f"(d[O+12]), "+f"(d[O+13]), "+f"(d[O+14]), "+f"(d[O+15]), "+f"(d[O+16]), "+f"(d[O+17]), "+f"(d[O+18]), "+f"(d[O+19]), "+f"(d[O+20]), "+f"(d[O+21]), "+f"(d[O+22]), "+f"(d[O+23]), "+f"(d[O+24]), "+f"(d[O+25]), "+f"(d[O+26]), "+f"(d[O+27]), "+f"(d[O+28]), "+f"(d[O+29]), "+f"(d[O+30]), "+f"(d[O+31]), "+f"(d[O+32]), "+f"(d[O+33]), "+f"(d[O+34]), "+f"(d[O+35]), "+f"(d[O+36]), "+f"(d[O+37]), "+f"(d[O+38]), "+f"(d[O+39]), "+f"(d[O+40]), "+f"(d[O+41]), "+f"(d[O+42]), "+f"(d[O+43]), "+f"(d[O+44]), "+f"(d[O+45]), "+f"(d[O+46]), "+f"(d[O+47]), "+f"(d[O+48]), "+f"(d[O+49]), "+f"(d[O+50]), "+f"(d[O+51]), "+f"(d[O+52]), "+f"(d[O+53]), "+f"(d[O+54]), "+f"(d[O+55]), "+f"(d[O+56]), "+f"(d[O+57]), "+f"(d[O+58]), "+f"(d[O+59]), "+f"(d[O+60]), "+f"(d[O+61]), "+f"(d[O+62]), "+f"(d[O+63])
   : "r"(a0), "r"(a1), "r"(a2), "r"(a3), "l"(db), "n"(TB));
  else if constexpr (ACC == 0) asm volatile("wgmma.mma_async.sync.aligned.m64n128k16.f32.bf16.bf16 {%0,%1,%2,%3,%4,%5,%6,%7,%8,%9,%10,%11,%12,%13,%14,%15,%16,%17,%18,%19,%20,%21,%22,%23,%24,%25,%26,%27,%28,%29,%30,%31,%32,%33,%34,%35,%36,%37,%38,%39,%40,%41,%42,%43,%44,%45,%46,%47,%48,%49,%50,%51,%52,%53,%54,%55,%56,%57,%58,%59,%60,%61,%62,%63}, {%64,%65,%66,%67}, %68, 0, 1, 1, %69;"
   : "=f"(d[O+0]), "=f"(d[O+1]), "=f"(d[O+2]), "=f"(d[O+3]), "=f"(d[O+4]), "=f"(d[O+5]), "=f"(d[O+6]), "=f"(d[O+7]), "=f"(d[O+8]), "=f"(d[O+9]), "=f"(d[O+10]), "=f"(d[O+11]), "=f"(d[O+12]), "=f"(d[O+13]), "=f"(d[O+14]), "=f"(d[O+15]), "=f"(d[O+16]), "=f"(d[O+17]), "=f"(d[O+18]), "=f"(d[O+19]), "=f"(d[O+20]), "=f"(d[O+21]), "=f"(d[O+22]), "=f"(d[O+23]), "=f"(d[O+24]), "=f"(d[O+25]), "=f"(d[O+26]), "=f"(d[O+27]), "=f"(d[O+28]), "=f"(d[O+29]), "=f"(d[O+30]), "=f"(d[O+31]), "=f"(d[O+32]), "=f"(d[O+33]), "=f"(d[O+34]), "=f"(d[O+35]), "=f"(d[O+36]), "=f"(d[O+37]), "=f"(d[O+38]), "=f"(d[O+39]), "=f"(d[O+40]), "=f"(d[O+41]), "=f"(d[O+42]), "=f"(d[O+43]), "=f"(d[O+44]), "=f"(d[O+45]), "=f"(d[O+46]), "=f"(d[O+47]), "=f"(d[O+48]), "=f"(d[O+49]), "=f"(d[O+50]), "=f"(d[O+51]), "=f"(d[O+52]), "=f"(d[O+53]), "=f"(d[O+54]), "=f"(d[O+55]), "=f"(d[O+56]), "=f"(d[O+57]), "=f"(d[O+58]), "=f"(d[O+59]), "=f"(d[O+60]), "=f"(d[O+61]), "=f"(d[O+62]), "=f"(d[O+63])
   : "r"(a0), "r"(a1), "r"(a2), "r"(a3), "l"(db), "n"(TB));
  else asm volatile("{\n.reg .pred p;\nsetp.ne.b32 p, %70, 0;\nwgmma.mma_async.sync.aligned.m64n128k16.f32.bf16.bf16 {%0,%1,%2,%3,%4,%5,%6,%7,%8,%9,%10,%11,%12,%13,%14,%15,%16,%17,%18,%19,%20,%21,%22,%23,%24,%25,%26,%27,%28,%29,%30,%31,%32,%33,%34,%35,%36,%37,%38,%39,%40,%41,%42,%43,%44,%45,%46,%47,%48,%49,%50,%51,%52,%53,%54,%55,%56,%57,%58,%59,%60,%61,%62,%63}, {%64,%65,%66,%67}, %68, p, 1, 1, %69;\n}"
   : "+f"(d[O+0]), "+f"(d[O+1]), "+f"(d[O+2]), "+f"(d[O+3]), "+f"(d[O+4]), "+f"(d[O+5]), "+f"(d[O+6]), "+f"(d[O+7]), "+f"(d[O+8]), "+f"(d[O+9]), "+f"(d[O+10]), "+f"(d[O+11]), "+f"(d[O+12]), "+f"(d[O+13]), "+f"(d[O+14]), "+f"(d[O+15]), "+f"(d[O+16]), "+f"(d[O+17]), "+f"(d[O+18]), "+f"(d[O+19]), "+f"(d[O+20]), "+f"(d[O+21]), "+f"(d[O+22]), "+f"(d[O+23]), "+f"(d[O+24]), "+f"(d[O+25]), "+f"(d[O+26]), "+f"(d[O+27]), "+f"(d[O+28]), "+f"(d[O+29]), "+f"(d[O+30]), "+f"(d[O+31]), "+f"(d[O+32]), "+f"(d[O+33]), "+f"(d[O+34]), "+f"(d[O+35]), "+f"(d[O+36]), "+f"(d[O+37]), "+f"(d[O+38]), "+f"(d[O+39]), "+f"(d[O+40]), "+f"(d[O+41]), "+f"(d[O+42]), "+f"(d[O+43]), "+f"(d[O+44]), "+f"(d[O+45]), "+f"(d[O+46]), "+f"(d[O+47]), "+f"(d[O+48]), "+f"(d[O+49]), "+f"(d[O+50]), "+f"(d[O+51]), "+f"(d[O+52]), "+f"(d[O+53]), "+f"(d[O+54]), "+f"(d[O+55]), "+f"(d[O+56]), "+f"(d[O+57]), "+f"(d[O+58]), "+f"(d[O+59]), "+f"(d[O+60]), "+f"(d[O+61]), "+f"(d[O+62]), "+f"(d[O+63])
   : "r"(a0), "r"(a1), "r"(a2), "r"(a3), "l"(db), "n"(TB), "r"(sd));
}

#define NEARLY 0
#define XAHEAD 3
#define HEADN 6
#define WBATCH 1
#define WB 8
#define WSLEEP 20
#define XSPREAD 4
#define NOSEND 0
#define MSPLIT 3
#define PFALL 1
#define L2PF 1
#define STAG 0
#define EPF 2
#define XNB 2
#define FNB 0
#define GNB 0
#define TH 4
#define PF0 4
#define FSPLIT 1
#define MGLU 1
#define SPC 2
#define TL 14
#define OUTV 0
#define SPACE 40
#define WPF 1
#define WAFTER 7
#define WPACE 0
#define GATE_AT 4
#define TPACE 40
#define PFMODE 0
#define MAPMODE 1
template <int V> struct IC { static constexpr int value = V; };
struct Maps { CUtensorMap x, ft, g64, u64, e, wr, wi, xs, ts, t, g32, u32, d224, o; };

constexpr int NCTA = 130;
constexpr int U = 16384;
constexpr int TB = 36864;
constexpr int OFF_RING = 8 * U, OFF_Z = 12 * U, OFF_XB = 12 * U, OFF_T = 13 * U, OFF_D = OFF_T;
constexpr int OFF_BAR = 14 * U, OFF_SP = OFF_BAR + 512, OFF_G = OFF_SP + 1024 + 128;
constexpr int SMEM_BYTES = OFF_G + 512;
constexpr int B_FX = 0, B_FA = 8, B_FT = 12, B_Z = 16, B_W = 24, B_HX = 25, B_TL = 26, B_HP = 27, B_WR = 30, B_E0 = 34;
constexpr int B_EA = 35, B_ET = 39, B_PZ = 43, B_RDY = 45, B_FE = 46;
constexpr int B_T = 50, B_XS = 51, B_G = 53, B_RD0 = 54, NBAR = 55;
__host__ __device__ constexpr int rslot(int n) { return n & 3; }
__host__ __device__ constexpr int rpar(int n) { return (n >> 2) & 1; }

__global__ void __cluster_dims__(2, 1, 1) __launch_bounds__(512, 1)
fused_kernel(Work* __restrict__ ws, const uint16_t* __restrict__ dtab, const __nv_bfloat16* __restrict__ w_r, const __nv_bfloat16* __restrict__ w_i,
             const __nv_bfloat16* __restrict__ gate_w, const __nv_bfloat16* __restrict__ x, __nv_bfloat16* __restrict__ out,
             const __grid_constant__ Maps maps) {
  extern __shared__ __align__(1024) uint8_t smem[];
  if (threadIdx.x < 32 && elect_one()) {
#pragma unroll
    for (int i = 0; i < PF0; i++) asm volatile("prefetch.tensormap [%0];" ::"l"((const char*)&maps + i * 128) : "memory");
  }
  const uint32_t sb = smem_u32(smem);
  const uint32_t bars = sb + OFF_BAR;
  const int tid = threadIdx.x, lane = tid & 31;
  const int warp = __shfl_sync(0xffffffffu, tid >> 5, 0);
  const bool helper = blockIdx.x >= 128;
  const int cl = (blockIdx.x >> 1) & 63, rank = blockIdx.x & 1;
  const int q4 = (cl & 1) | ((cl >> 2) & 2), rb = ((cl >> 1) & 3) | ((cl >> 4) << 2);
  const int j = 2 * q4 + rank;
  const int f_full = 448 * q4 + (rank ? 256 : 0);
  const int f_half = 448 * q4 + (rank ? 224 : 192);
  const int kg = 2 * j + (rb >> 3), tn = rb & 7;

  if (tid == 64) { PROF_EV(0); PROF_CK(40); }
  if (warp < 8) {
    if (!helper && tid < 32) {
      const int r = 16 * j + (tid & 15);
      asm volatile("prefetch.global.L2 [%0];" ::"l"(x + (size_t)(2 * rb + (r >> 6) + 32 * (r & 63)) * 512 + 64 * (tid >> 4)));
    }
    asm volatile("barrier.cluster.arrive.relaxed.aligned;" ::: "memory");
    asm volatile("setmaxnreg.inc.sync.aligned.u32 192;");
    if (!helper) {
      const int wg = warp >> 2, w = warp & 3, g = lane >> 2;
      const bool elect = (tid & 127) == 0;
      float cX[32], cA[64], cB[64], cC[64], ci[64], ct[64];
      const int zero = blockIdx.x >> 16;
      uint32_t h[56], yf[16];
      const uint32_t d0 = (sb & 0x3FFFF) >> 4;
      const uint32_t dK = d0 | (1u << 16), dN = d0 | (512u << 16);
      const uint32_t dX = dK + wg * 512;
      constexpr uint32_t RING = OFF_RING >> 4;
      auto waitA = [&](int n) { mbar_wait(bars + 8 * (B_FA + rslot(n)), rpar(n)); };
      auto freeA = [&](int n) { mbar_arrive_if(elect, bars + 8 * (B_EA + rslot(n))); };
      auto nop = [] {};

      asm volatile("bar.sync 0, 384;" ::: "memory");
#pragma unroll 1
      for (int i = 0; i < 4; i++) {
        const uint64_t dx = d128(dX + i * 2048), df = d128(dK + (OFF_XB >> 4) + (i & 1) * 1024);
        mbar_wait(bars + 8 * (B_FX + 2 * i), 0);
        wg_fence();
        mma_ss64<0, 0, 2>(cX, df, dx, i);
        mma_ss64<0, 0, 1>(cX, df + 2, dx + 2);
        wg_commit(); wg_wait<1>();
        mbar_arrive_if(elect && i, bars + 8 * (B_EA + rslot(i - 1)));
        mma_ss64<0, 0, 1>(cX, df + 4, dx + 4);
        mma_ss64<0, 0, 1>(cX, df + 6, dx + 6);
        if (i == 0 && tid == 0) PROF_EV(1);
        mbar_wait(bars + 8 * (B_FX + 2 * i + 1), 0);
        wg_fence();
#pragma unroll
        for (int k = 0; k < 4; k++) mma_ss64<0, 0, 1>(cX, df + (512 + k * 2), dx + (1024 + k * 2));
        wg_commit();
        waitA(i);
        wg_fence();
        const uint64_t da = d128(dX + i * 1024), db = d128(dN + RING + i * 1024);
        mma_ss128<0, 1, 2>(cA, da, db, i);
        wg_commit(); wg_wait<1>();
        mbar_arrive_if(elect, bars + 8 * (B_FE + i));
#pragma unroll
        for (int k = 1; k < 4; k++) mma_ss128<0, 1, 1>(cA, da + k * 2, db + k * 128);
        wg_commit();
      }
      fence_regs<0, 32>(cX);
#pragma unroll
      for (int e = 0; e < 16; e++) yf[e] = pack_pin(cX[2 * e], cX[2 * e + 1]);
      if (tid == 0) { PROF_EV(2); PROF_CK(42); }
      {
        waitA(4); mbar_wait(bars + 8 * B_E0, 0);
        const uint64_t de = d128(dN + (wg ? RING : OFF_XB >> 4));
        wg_fence();
        mma_rs128<0, 1, 0>(cB, yf[0], yf[1], yf[2], yf[3], de);
        wg_commit();
        wg_wait<1>();
        freeA(3);
#pragma unroll
        for (int k = 1; k < 4; k++) mma_rs128<0, 1, 1>(cB, yf[4 * k], yf[4 * k + 1], yf[4 * k + 2], yf[4 * k + 3], de + k * 128);
        wg_commit();
      }
      bool rel = false;
      auto acquire = [&](int n) {
        rel = elect;
        if (!mbar_try(bars + 8 * (B_FA + rslot(n)), rpar(n))) { wg_wait<0>(); freeA(n - 1); rel = false; waitA(n); }
      };
      auto freeP = [&](int n) { mbar_arrive_if(rel, bars + 8 * (B_EA + rslot(n - 1))); };
      auto ffn_step = [&](auto first, auto split, float (&acc)[64], int n, int kb, auto done, auto work) {
        constexpr int SPLIT = decltype(split)::value;
        acquire(n);
        wg_fence();
        const uint64_t dx = d128(dX + kb * 1024), db = d128(dN + RING + rslot(n) * 1024);
        mma_ss128<0, 1, decltype(first)::value>(acc, dx, db, kb);
#pragma unroll
        for (int k = 1; k < SPLIT; k++) mma_ss128<0, 1, 1>(acc, dx + k * 2, db + k * 128);
        wg_commit();
        work();
        wg_wait<1>();
        freeP(n);
        done();
        if (SPLIT < 4) {
          wg_fence();
#pragma unroll
          for (int k = SPLIT; k < 4; k++) mma_ss128<0, 1, 1>(acc, dx + k * 2, db + k * 128);
          wg_commit();
        }
      };
      {
        const int s0 = 2 * rb + wg, kr = 2 * ((s0 & 1) | ((s0 & 4) >> 1));
        const int m = lane >> 3, r = lane & 7;
        const uint32_t a0 = sb + OFF_XB + wg * 8192 + (((w >> 1) * 8 + (m >> 1)) * 2 + (w & 1)) * 256 + (m & 1) * 128 + ((r ^ (kr + (m & 1))) << 4);
        ffn_step(IC<1>(), IC<4>(), cA, 5, 4, [&] { fence_regs<0, 64>(cB); }, nop);
        asm volatile("bar.sync 5, 256;" ::: "memory");
        auto stage = [&](int i) {
          stsm4t(a0 + i * 1024, pack_bf16(cB[8 * i] - cB[34 + 8 * i], cB[8 * i + 1] - cB[35 + 8 * i]),
                 pack_bf16(cB[32 + 8 * i] + cB[8 * i + 2], cB[33 + 8 * i] + cB[8 * i + 3]),
                 pack_bf16(cB[8 * i + 4] - cB[38 + 8 * i], cB[8 * i + 5] - cB[39 + 8 * i]),
                 pack_bf16(cB[36 + 8 * i] + cB[8 * i + 6], cB[37 + 8 * i] + cB[8 * i + 7]));
          if (j == 0 && w == 0) {
            const uint32_t a1 = r ? sb + OFF_SP + 1024 : sb + OFF_SP + wg * 512 + (m & 1) * 256 + (m >> 1) * 128;
#pragma unroll
            for (int n = 2 * i; n < 2 * i + 2; n++)
              asm volatile("stmatrix.sync.aligned.m8n8.x4.shared.b16 [%0], {%1,%2,%3,%4};" ::"r"(a1 + ((n ^ (kr + (m >> 1)) ^ r) << 4)),
                           "r"(pack_bf16(cB[4 * n], cB[4 * n + 1])), "r"(pack_bf16(cB[4 * n + 2], cB[4 * n + 3])),
                           "r"(pack_bf16(cB[32 + 4 * n], cB[33 + 4 * n])), "r"(pack_bf16(cB[34 + 4 * n], cB[35 + 4 * n])) : "memory");
          }
        };
        auto publish = [&] {
          asm volatile("fence.proxy.async.shared::cta;" ::: "memory");
          __syncwarp();
          mbar_arrive_if(lane == 0, bars + 8 * (B_XS + wg));
          if (tid == 0) PROF_EV(3);
        };
        stage(0);
        ffn_step(IC<1>(), IC<FSPLIT>(), cA, 6, 5, nop, nop);
        stage(1);
        ffn_step(IC<1>(), IC<FSPLIT>(), cA, 7, 6, nop, nop);
        stage(2);
        ffn_step(IC<1>(), IC<2>(), cA, 8, 7, [&] { stage(3); }, nop);
        publish();
      }
      float g0 = 0.f, g1 = 0.f;
      uint32_t tag = 0;
      uint32_t ob[2] = {0, 0};
      auto glu = [&](auto& acc, int half, int ho, int i0, int i1) {
#pragma unroll
        for (int i = i0; i < i1; i++)
          asm volatile("{\n.reg .b32 a, b;\ncvt.rn.relu.bf16x2.f32 a, %2, %1;\ncvt.rn.bf16x2.f32 b, %4, %3;\nmul.rn.bf16x2 a, a, b;\nmul.rn.bf16x2 %0, a, %5;\n}"
                       : "=r"(h[ho + i]) : "f"(acc[2 * i]), "f"(acc[2 * i + 1]), "f"(acc[half + 2 * i]), "f"(acc[half + 1 + 2 * i]), "r"(ob[i & 1]) : "memory");
      };
      ffn_step(IC<2>(), IC<1>(), cB, 9, zero, nop, nop);
#pragma unroll 1
      for (int kb = 1; kb < 8; kb++)
        ffn_step(IC<1>(), IC<FSPLIT>(), cB, 9 + kb, kb, nop, [&] {
          if (kb == 4 + 2 * wg) {
            mbar_wait(bars + 8 * B_G, 0);
            const uint32_t gb0 = *(const uint32_t*)(smem + OFF_G + (wg * 64 + w * 16 + g) * 4), gb1 = *(const uint32_t*)(smem + OFF_G + (wg * 64 + w * 16 + g + 8) * 4);
            tag = gb0 & 1; g0 = __uint_as_float(gb0 & ~1u); g1 = __uint_as_float(gb1 & ~1u);
            ob[0] = pack_bf16(1.0f - g0, 1.0f - g0); ob[1] = pack_bf16(1.0f - g1, 1.0f - g1);
            glu(cA, 32, 0, 0, 16);
          }
        });
      if (tid == 0) { PROF_EV(4); PROF_CK(43); }
      auto m_step = [&](auto first, int i) {
        acquire(17 + i);
        wg_fence();
        const uint64_t dx = d128(dX + i * 2048), dm = d64(dN + RING + rslot(17 + i) * 1024);
        mma_ss64<0, 1, decltype(first)::value>(ct, dx, dm);
#pragma unroll
        for (int k = 1; k < MSPLIT; k++) mma_ss64<0, 1, 1>(ct, dx + ((k >> 2) * 1024 + (k & 3) * 2), dm + k * 64);
        wg_commit();
        wg_wait<1>();
        freeP(17 + i);
        wg_fence();
#pragma unroll
        for (int k = MSPLIT; k < 8; k++) mma_ss64<0, 1, 1>(ct, dx + ((k >> 2) * 1024 + (k & 3) * 2), dm + k * 64);
        wg_commit();
      };
      m_step(IC<0>(), 0);
#pragma unroll 1
      for (int i = 1; i < 5; i++) {
        if (i == 1 + 2 * wg) glu(cB, 32, 16, 0, 16);
        if (i < 4) m_step(IC<1>(), i);
      }
      if (tid == 0) { PROF_EV(5); PROF_CK(44); }
      ffn_step(IC<0>(), IC<1>(), cC, 21, 0, nop, nop);
#pragma unroll 1
      for (int kb = 1; kb < 8; kb++)
        ffn_step(IC<1>(), IC<FSPLIT>(), cC, 21 + kb, kb, [&] { mbar_arrive_if(elect && !(kb & 1), bars + 8 * (B_ET + (kb >> 1) - 1)); }, [&] {
          if (kb == 1 + wg) glu(ct, 16, 48, 0, 8);
        });

      auto twait = [&](uint32_t bar, uint32_t par, int) { mbar_wait(bar, par); };
      const int fo = warp * 128 + lane;
      auto fetch = [&](uint4 (&pv)[4], int z) {
        twait(bars + 8 * (z < 4 ? B_Z + 2 * z + wg : B_HP + z - 4), 0, 8 + z);
        const uint8_t* src = smem + (z < 4 ? OFF_Z - z * U : z == 4 ? OFF_T : (z - 5) * U) + fo * 16;
#pragma unroll
        for (int i = 0; i < 4; i++) pv[i] = *(const uint4*)(src + i * 512);
      };
      auto check = [&](uint4 (&pv)[4], int z) {
#pragma unroll 1
        for (int n = 0; __any_sync(0xffffffffu, ((pv[0].x ^ tag) | (pv[1].x ^ tag) | (pv[2].x ^ tag) | (pv[3].x ^ tag)) & 1); n++) {
#pragma unroll
          for (int i = 0; i < 4; i++) pv[i] = ld_x4(ws->part + (size_t)((rb * 8 + j) * 3 + z - 4) * 1024 + fo + i * 32);
          if (n > (1 << 21)) __trap();
        }
#pragma unroll
        for (int i = 0; i < 4; i++) pv[i].x &= ~1u;
      };
      const uint32_t peerZ = mapa(sb + OFF_Z + fo * 16, rank ^ 1), peerB = mapa(bars + 8 * (B_Z + wg), rank ^ 1);
      auto tile_mma = [&](auto off, int t, int k0, int k1, int init) {
        constexpr int O = decltype(off)::value;
        const uint64_t db = d128(dN + (t & 3) * (TB >> 4)), dw = db + rank * 256, dm = db + (rank ? 0 : 1536);
#pragma unroll
        for (int k = k0; k < k1; k++) {
          if (k == 0) mma_rs64<O, 1, 2>(ct, h[0], h[1], h[2], h[3], dw, init);
          else if (k < 14) mma_rs64<O, 1, 1>(ct, h[4 * k], h[4 * k + 1], h[4 * k + 2], h[4 * k + 3], k < 12 ? dw + k * 128 : dm + (k - 12) * 128);
          else mma_rs64<O, 1, 1>(ct, yf[4 * k - 56], yf[4 * k - 55], yf[4 * k - 54], yf[4 * k - 53], db + k * 128);
        }
      };
      uint4 pv[4] = {};
      auto tile = [&](auto off, int t) {
        constexpr int P = 32 - decltype(off)::value;
        const bool grid = t >= 4 && t < 7, pre = t >= 3 && t != 6;
        const int zo = grid ? t - 4 : t == 7 ? 3 : t - 1, z = t - 3;
        const int owner = rb * 8 + 2 * ((q4 + zo + 1) & 3) + rank;
        uint4* dst = ws->part + (size_t)(owner * 3 + zo) * 1024 + fo;
        const uint32_t src = sb + (z < 4 ? OFF_Z - z * U : OFF_T) + fo * 16;
        twait(bars + 8 * (B_FT + (t & 3)), t >> 2, t);
        wg_fence();
        tile_mma(off, t, 0, TH, zero);
        wg_commit();
        wg_wait<1>();
        mbar_arrive_if(elect && t < 6, bars + 8 * (B_ET + t - 1));
        if (t < 3) twait(bars + 8 * (t == 1 ? B_RD0 : B_RDY), 0, 14 + t);
        fence_regs<P, 32>(ct);
#pragma unroll
        for (int i = 0; i < 4; i++) {
          pv[i].x = (add_bf2(pv[i].x, pack_bf16(ct[P + 8 * i], ct[P + 8 * i + 1])) & ~(uint32_t)grid) | (tag & grid);
          pv[i].y = add_bf2(pv[i].y, pack_bf16(ct[P + 8 * i + 2], ct[P + 8 * i + 3]));
          pv[i].z = add_bf2(pv[i].z, pack_bf16(ct[P + 8 * i + 4], ct[P + 8 * i + 5]));
          pv[i].w = add_bf2(pv[i].w, pack_bf16(ct[P + 8 * i + 6], ct[P + 8 * i + 7]));
        }
        if (grid) {
#pragma unroll
          for (int i = 0; i < 4; i++)
            asm volatile("st.relaxed.gpu.global.v4.u32 [%0], {%1,%2,%3,%4};" ::"l"(dst + i * 32), "r"(pv[i].x), "r"(pv[i].y), "r"(pv[i].z), "r"(pv[i].w) : "memory");
          hint_add_if(lane == 0, &ws->cntP[32 * owner + 8 * zo]);
        }
        auto share = [&](int i) {
          asm volatile("st.async.weak.shared::cluster.mbarrier::complete_tx::bytes.v4.b32 [%0], {%2,%3,%4,%5}, [%1];" ::"r"(peerZ - zo * U + i * 512),
                       "r"(peerB + 16 * zo), "r"(pv[i].x), "r"(pv[i].y), "r"(pv[i].z), "r"(pv[i].w) : "memory");
        };
        if (P == 0 && t == 7) { share(1); share(2); share(3); }
#pragma unroll
        for (int i = 0; i < 4; i++) {
          if (i == 0 ? !grid : t < 4) share(i);
          if (0)
            asm volatile("st.async.weak.shared::cluster.mbarrier::complete_tx::bytes.v4.b32 [%0], {%2,%3,%4,%5}, [%1];" ::"r"(peerZ - zo * U + i * 512),
                         "r"(peerB + 16 * zo), "r"(pv[i].x), "r"(pv[i].y), "r"(pv[i].z), "r"(pv[i].w) : "memory");
          wg_fence();
          tile_mma(off, t, TH + SPC * i, i < 3 ? TH + SPC * i + SPC : TL, 0);
        }
        wg_commit();
        if (pre) twait(bars + 8 * (z < 4 ? B_Z + 2 * z + wg : B_HP), 0, 8 + z);
        wg_fence();
#pragma unroll
        for (int i = 0; i < 4; i++) {
          asm volatile("{\n.reg .pred p;\nsetp.ne.b32 p, %5, 0;\nmov.b32 %0, 0;\nmov.b32 %1, 0;\nmov.b32 %2, 0;\nmov.b32 %3, 0;\n@p ld.shared.v4.u32 {%0,%1,%2,%3}, [%4];\n}"
                       : "=r"(pv[i].x), "=r"(pv[i].y), "=r"(pv[i].z), "=r"(pv[i].w) : "r"(src + i * 512), "r"((int)pre) : "memory");
          tile_mma(off, t, TL + i, i < 3 ? TL + 1 + i : 18, 0);
        }
        wg_commit();
      };
      asm volatile("barrier.cluster.wait.aligned;" ::: "memory");
      twait(bars + 8 * B_FT, 0, 0);
      wg_fence();
      tile_mma(IC<0>(), 0, 0, 5, zero);
      wg_commit();
      wg_wait<1>();
      mbar_arrive_if(elect, bars + 8 * (B_ET + 3));
      glu(cC, 32, 32, 0, 8);
      waitA(29 + wg);
      wg_fence();
      tile_mma(IC<0>(), 0, 5, 8, 0);
      tile_mma(IC<0>(), 0, 12, 14, 0);
      wg_commit();
      glu(cC, 32, 32, 8, 16);
      if (tid == 0) PROF_EV(6);
      if (tid == 128) PROF_EV(27);
      mbar_wait(bars + 8 * (j == 0 ? B_T : B_TL), 0);
      if (tid == 0) { PROF_EV(7); PROF_CK(45); }
      wg_fence();
      {
        const uint64_t dt = d128(dN + (OFF_T >> 4) + wg * 512), de = d128(dK + RING + (1 + wg) * 1024);
        mma_ss64<0, 1, 0>(ci, de, dt);
        mma_ss64<32, 1, 0>(ci, de + 512, dt);
#pragma unroll
        for (int k = 1; k < 4; k++) {
          mma_ss64<0, 1, 1>(ci, de + k * 2, dt + k * 128);
          mma_ss64<32, 1, 1>(ci, de + (512 + k * 2), dt + k * 128);
        }
        wg_commit();
      }
      tile_mma(IC<0>(), 0, 8, 12, 0);
      wg_commit();
      wg_wait<1>();
      if (elect) asm volatile("mbarrier.arrive.shared::cluster.b64 _, [%0];" ::"r"(mapa(bars + 8 * B_RDY, rank ^ 1)) : "memory");
      mbar_arrive_if(elect, bars + 8 * (B_PZ + 1));
      fence_regs<0, 64>(ci);
#pragma unroll
      for (int i = 0; i < 16; i++) {
        const float gg = ((i & 1) ? g1 : g0) * (2.0f / (2048.0f * 512.0f));
        if (i & 2) yf[i] = pack_pin((ci[2 * i] - ci[28 + 2 * i]) * gg, (ci[2 * i + 1] - ci[29 + 2 * i]) * gg);
        else yf[i] = pack_pin((ci[2 * i] + ci[36 + 2 * i]) * gg, (ci[2 * i + 1] + ci[37 + 2 * i]) * gg);
      }
      wg_fence();
      tile_mma(IC<0>(), 0, 14, 18, 0);
      wg_commit();
      if (tid == 0) PROF_EV(8);
      if (tid == 128) PROF_EV(28);
#pragma unroll 1
      for (int t = 1;; t += 2) {
        tile(IC<32>(), t);
        if (t == 7) break;
        tile(IC<0>(), t + 1);
      }
      if (tid == 0) { PROF_EV(9); PROF_CK(46); }
      if (tid == 128) PROF_EV(29);
      {
        uint4 p1[4], p2[4];
        auto acc4 = [&](uint4 (&d)[4], const uint4 (&a)[4]) {
#pragma unroll
          for (int i = 0; i < 4; i++) { d[i].x = add_bf2(d[i].x, a[i].x); d[i].y = add_bf2(d[i].y, a[i].y); d[i].z = add_bf2(d[i].z, a[i].z); d[i].w = add_bf2(d[i].w, a[i].w); }
        };
        fetch(p1, 5);
        fetch(p2, 3);
        if (tid == 0) PROF_EV(25);
        check(pv, 4); check(p1, 5);
        acc4(pv, p1); acc4(pv, p2);
        wg_wait<0>();
        fence_regs<32, 32>(ct);
#pragma unroll
        for (int i = 0; i < 4; i++) {
          pv[i].x = pack_pin(ct[32 + 8 * i] + bf_lo(pv[i].x), ct[33 + 8 * i] + bf_hi(pv[i].x)); pv[i].y = pack_pin(ct[34 + 8 * i] + bf_lo(pv[i].y), ct[35 + 8 * i] + bf_hi(pv[i].y));
          pv[i].z = pack_pin(ct[36 + 8 * i] + bf_lo(pv[i].z), ct[37 + 8 * i] + bf_hi(pv[i].z)); pv[i].w = pack_pin(ct[38 + 8 * i] + bf_lo(pv[i].w), ct[39 + 8 * i] + bf_hi(pv[i].w));
        }
        if (tid == 0) PROF_EV(14);
        fetch(p2, 6);
        if (tid == 0) PROF_EV(24);
        check(p2, 6);
        acc4(pv, p2);
        const uint32_t stg = sb + OFF_T + warp * 2048;
        const int mr = (lane & 7) + ((lane >> 3) & 1) * 8, mc = lane >> 4;
#pragma unroll
        for (int i = 0; i < 4; i++)
          asm volatile("stmatrix.sync.aligned.m8n8.x4.shared.b16 [%0], {%1,%2,%3,%4};" ::"r"(stg + mr * 128 + (((2 * i + mc) ^ (mr & 7)) << 4)), "r"(pv[i].x),
                       "r"(pv[i].y), "r"(pv[i].z), "r"(pv[i].w) : "memory");
        asm volatile("fence.proxy.async.shared::cta;" ::: "memory");
        __syncwarp();
        if (elect_one()) {
          asm volatile("cp.async.bulk.tensor.3d.global.shared::cta.bulk_group [%0, {%2, %3, %4}], [%1];" ::"l"(&maps.o), "r"(stg), "r"(64 * j),
                       "r"(16 * w), "r"(2 * rb + wg) : "memory");
          asm volatile("cp.async.bulk.commit_group;\ncp.async.bulk.wait_group.read 0;" ::: "memory");
        }
      }
      if (tid == 0) { PROF_EV(15); PROF_CK(41); }
      if (tid == 128) PROF_EV(30);
    }
  } else if (warp < 12) {
    asm volatile("setmaxnreg.dec.sync.aligned.u32 104;");
    asm volatile("barrier.cluster.arrive.relaxed.aligned;" ::: "memory");
    const int t = tid - 256, w = warp - 8;
    const uint32_t ep = ld_x1(&ws->epoch[blockIdx.x * 8]);
    const uint32_t tag = (ep + 1) & 1;
    auto w_issue = [&](const CUtensorMap* m) {

      if (elect_one()) { mbar_expect_tx(bars + 8 * (B_WR + w), 3072); tma4d(sb + OFF_T + w * 3072, m, bars + 8 * (B_WR + w), 16 * kg, 0, 2 * w, tn); }

          __syncwarp();
    };
    auto gate_rows = [&] {
      const int r = 16 * j + 4 * w + (lane >> 3);
      const uint4* pg = (const uint4*)gate_w + (lane & 7);
      {
        float a = 0.f;
        asm volatile("bar.sync 4, 256;" ::: "memory");
#pragma unroll 1
        for (int hf = 0; hf < 2; hf++) {
          uint4 v[4], u[4];
#pragma unroll
          for (int kb = 0; kb < 4; kb++) v[kb] = __ldg(pg + (4 * hf + kb) * 8);
          mbar_wait(bars + 8 * (B_FE + 1 + 2 * hf), 0);
          if (hf) w_issue(&maps.wr);
#pragma unroll
          for (int kb = 0; kb < 4; kb++) u[kb] = *(const uint4*)(smem + (4 * hf + kb) * U + r * 128 + (((lane ^ r) & 7) << 4));
#pragma unroll
          for (int kb = 0; kb < 4; kb++) {
            const uint32_t uu[4] = {u[kb].x, u[kb].y, u[kb].z, u[kb].w}, vv[4] = {v[kb].x, v[kb].y, v[kb].z, v[kb].w};
#pragma unroll
            for (int e = 0; e < 4; e++) {
              uint32_t pr;
              asm("mul.rn.bf16x2 %0, %1, %2;" : "=r"(pr) : "r"(uu[e]), "r"(vv[e]));
              a += bf_lo(pr) + bf_hi(pr);
            }
          }
        }
#pragma unroll
        for (int o = 4; o; o >>= 1) a += __shfl_xor_sync(0xffffffffu, a, o);
        if ((lane & 7) == 0)
          asm volatile("st.relaxed.gpu.global.u32 [%0], %1;" ::"l"(ws->gate + rb * 128 + r),
                       "r"(pack_bf16(0.f, __fdividef(1.0f, 1.0f + __expf(-bf_lo(pack_bf16(a, 0.f))))) | tag) : "memory");
        if (t == 0) PROF_EV(18);
      }
    };
    {
      const int g = lane >> 2, q = lane & 3;
      uint32_t wf[32];
      if (!helper) {
        gate_rows();
        const uint32_t wa = sb + OFF_T + w * (3072 + 4) + q * 48 + g * 2;
#pragma unroll 1
        for (int ri = 0; ri < 2; ri++) {
          mbar_wait(bars + 8 * (B_WR + w), ri);
#pragma unroll
          for (int n2 = 0; n2 < 32 / WB; n2++) {
            uint32_t v[WB];
#pragma unroll
            for (int i = 0; i < WB; i++) {
              const int e = n2 * WB + i;
              asm volatile("ld.shared.u16 %0, [%1];" : "=r"(v[i]) : "r"(wa + ((e >> 1) & 7) * 192 + (e & 1) * (1536 + 2) + (e >> 4) * 16) : "memory");
            }
#pragma unroll
            for (int i = 0; i < WB; i++) wf[n2 * WB + i] = __byte_perm(wf[n2 * WB + i], v[i], 0x5432);
            if (WSLEEP) { asm volatile("nanosleep.u32 %0;" ::"r"(WSLEEP + (v[WB - 1] >> 16)) : "memory"); }
          }
          __syncwarp();
          if (ri == 0) w_issue(&maps.wi);
        }
        asm volatile("bar.sync 1, 128;" ::: "memory");
        if (t == 0) PROF_EV(11);
      } else {
        asm volatile("bar.sync 4, 256;" ::: "memory");
        hint_wait(&ws->cntW[0], (ep + 1) * 128u);
        const uint32_t t0 = (uint32_t)clock();
#pragma unroll 1
        for (;;) {
          uint32_t bad = 0;
#pragma unroll
          for (int i = 0; i < 32; i++) {
            const float2 v = ld_x2((const float2*)ws->Wh + (i >> 4) * 2048 + 16 * w + g + 8 * (i & 1) + 64 * q + ((i >> 1) & 7) * 256);
            wf[i] = __float_as_uint(v.x); bad |= __float_as_uint(v.y) ^ tag;
          }
          if (!__any_sync(0xffffffffu, bad & 1)) break;
          spin_guard(t0);
        }
        if (t == 0) PROF_EV(11);
      }
      if (w == 0 && elect_one()) { mbar_expect_tx(bars + 8 * B_W, 8192); bulk_load(sb + OFF_D, dtab, 8192, bars + 8 * B_W); }
      asm volatile("barrier.cluster.wait.aligned;" ::: "memory");
      mbar_wait(bars + 8 * B_W, 0);
      mbar_wait(bars + 8 * B_HX, 0);
      if (t == 0) PROF_EV(12);
      const uint32_t dd = (sb & 0x3FFFF) >> 4;
      const uint64_t dF = d128((dd + (OFF_D >> 4)) | (512u << 16)), dI = d128((dd + (OFF_D >> 4)) | (1u << 16)), dA = d128((dd + (OFF_XB >> 4)) | (512u << 16));
      float az[32];
      const int zero = blockIdx.x >> 16;
      uint32_t pf[32];
#pragma unroll
      for (int mt = 0; mt < 2; mt++) {
        wg_fence();
        if (mt == 0) mma_ss64<0, 3, 0>(az, dA, dF);
        else mma_ss64<0, 3, 2>(az, dA + 512, dF, zero);
#pragma unroll
        for (int k = 1; k < 4; k++) mma_ss64<0, 3, 1>(az, dA + (mt * 512 + k * 128), dF + k * 128);
        wg_commit();
        wg_wait<0>();
        fence_regs<0, 32>(az);
#pragma unroll
        for (int i = 0; i < 16; i++) {
          const float wr = bf_lo(wf[16 * mt + i]), wi = bf_hi(wf[16 * mt + i]);
          pf[16 * mt + i] = pack_pin(fmaf(az[2 * i], wr, -az[2 * i + 1] * wi), fmaf(az[2 * i], wi, az[2 * i + 1] * wr));
        }
      }
      if (t == 0) PROF_EV(16);
      {
        const int m = lane >> 3, r = lane & 7;
        const int sl = 2 * (m >> 1) + ((r >> 1) & 1) + 4 * (r >> 2);
        const uint32_t a0 = sb + OFF_XB + (2 * w + (m & 1)) * 2048 + sl * 64;
        uint32_t pk[16];
#pragma unroll
        for (int mt = 0; mt < 3; mt++) {
          if (mt < 2) {
            wg_fence();
            mma_rs64<0, 0, 2>(az, pf[16 * mt], pf[16 * mt + 1], pf[16 * mt + 2], pf[16 * mt + 3], dI, mt ? (int)helper : zero);
#pragma unroll
            for (int k = 1; k < 4; k++) mma_rs64<0, 0, 1>(az, pf[16 * mt + 4 * k], pf[16 * mt + 4 * k + 1], pf[16 * mt + 4 * k + 2], pf[16 * mt + 4 * k + 3], dI + k * 2);
            wg_commit();
          }
          if (mt > 0 && !helper) {
#pragma unroll
            for (int i = 0; i < 4; i++) stsm4t(a0 + ((((mt - 1) * 2 + (r & 1)) ^ (sl >> 1)) << 4) + i * 512, pk[4 * i], pk[4 * i + 1], pk[4 * i + 2], pk[4 * i + 3]);
          }
          if (mt < 2) {
            wg_wait<0>();
            fence_regs<0, 32>(az);
#pragma unroll
            for (int i = 0; i < 16; i++) pk[i] = pack_pin(az[2 * i], az[2 * i + 1]);
          }
        }
      }
      if (helper) {
#pragma unroll
        for (int i = 0; i < 16; i++) {
          const int n = i >> 1, s0 = 8 * (n >> 1) + 2 * (n & 1) + (q & 1) + 4 * (q >> 1);
          if ((n & 1) == (int)(blockIdx.x & 1)) st_u2(ws->Ts + s0 * 64 + 16 * w + g + 8 * (i & 1), pack_bf16(az[2 * i], az[2 * i + 1]), tag);
        }
        __syncwarp();
        hint_add_if(lane == 0, &ws->cntH[0]);
        if (t == 0) { ws->epoch[blockIdx.x * 8] = ep + 1; PROF_EV(13); }
      } else {
        asm volatile("fence.proxy.async.shared::cta;" ::: "memory");
        __syncwarp();
        if (elect_one()) {
          if (t == 0) PROF_EV(17);
          if (SPACE) __nanosleep(SPACE * w);
          asm volatile("cp.async.bulk.tensor.3d.global.shared::cta.bulk_group [%0, {%2, %3, %4}], [%1];" ::"l"(&maps.ts), "r"(sb + OFF_XB + w * 4096),
                       "r"(32 * kg), "r"(0), "r"(8 * tn + 2 * w) : "memory");
          bulk_done_signal(&ws->cntT[32 * j]);
          asm volatile("mbarrier.arrive.shared::cluster.b64 _, [%0];" ::"r"(mapa(bars + 8 * B_RD0, rank ^ 1)) : "memory");
          if (t == 96) PROF_EV(13);
        }
        __syncwarp();
        if (j == 0) {
          hint_wait(&ws->cntH[0], (ep + 1) * 8u);
          const uint32_t t0 = (uint32_t)clock();
          float2 v;
          do { v = ld_x2((const float2*)ws->Ts + 2 * rb * 64 + t); spin_guard(t0); } while (__any_sync(0xffffffffu, (__float_as_uint(v.y) ^ tag) & 1));
          mbar_wait(bars + 8 * B_TL, 0);
          const uint32_t u = __float_as_uint(v.x);
          *(uint16_t*)(smem + OFF_T + t * 128 + ((t & 7) << 4)) = (uint16_t)u;
          *(uint16_t*)(smem + OFF_T + t * 128 + (((t & 7) ^ 1) << 4)) = (uint16_t)(u >> 16);
          asm volatile("fence.proxy.async.shared::cta;" ::: "memory");
          __syncwarp();
          mbar_arrive_if(lane == 0, bars + 8 * B_T);
        }
      }
    }
  } else {
    asm volatile("setmaxnreg.dec.sync.aligned.u32 24;");
    auto xf_load = [&](int q) {
      const uint32_t fb = bars + 8 * (B_FX + q);
      mbar_expect_tx(fb, U + 8192);
      tma3d(sb + q * U, &maps.x, fb, 64 * q, 0, 2 * rb);
      if (q >= 4) mbar_wait(bars + 8 * (B_FE + ((q - 4) >> 1)), 0);
      tma2d(sb + OFF_XB + (q & 3) * 8192, &maps.ft, fb, 64 * q, 64 * j);
    };
    if (elect_one()) {
      if (warp == 14) {
#pragma unroll
        for (int i = 0; i < B_FT; i++) mbar_init(bars + 8 * i, 1);
        asm volatile("fence.mbarrier_init.release.cluster;" ::: "memory");
        if (!helper) {
#pragma unroll 1
          for (int n = 0; n < 2; n++) {
            const uint32_t fb = bars + 8 * (B_FA + n);
            xf_load(2 * n); xf_load(2 * n + 1);
            mbar_expect_tx(fb, U);
            tma2d(sb + OFF_RING + n * U, &maps.g64, fb, f_full, 64 * n);
            tma2d(sb + OFF_RING + n * U + 8192, &maps.u64, fb, f_full, 64 * n);
          }
        }
      } else if (warp == 15) {
#pragma unroll
        for (int i = B_FT; i < NBAR; i++) mbar_init(bars + 8 * i, i < B_EA ? 1 : i < B_T ? 2 : 4);
#pragma unroll
        for (int i = 0; i < 8; i++) mbar_expect_tx(bars + 8 * (B_Z + i), U / 2);
        asm volatile("fence.mbarrier_init.release.cluster;" ::: "memory");
        asm volatile("fence.proxy.async.shared::cta;" ::: "memory");
      }
    }
    __syncwarp();
    asm volatile("bar.arrive 0, 384;" ::: "memory");
    asm volatile("bar.arrive 4, 256;" ::: "memory");
    __syncwarp();
    asm volatile("barrier.cluster.arrive.relaxed.aligned;" ::: "memory");
    asm volatile("bar.sync 3, 128;" ::: "memory");
    if (warp == 15 && !helper) {
        mbar_wait(bars + 8 * B_FE, 0);
        const uint32_t tag = (ld_x1(&ws->epoch[blockIdx.x * 8]) + 1) & 1;
        const int c = lane >> 4, jj = 16 * blockIdx.x + (lane & 15), jm = (2048 - jj) & 2047;
        const unsigned short* pr = (const unsigned short*)w_r + 256 * c;
        const unsigned short* pi = (const unsigned short*)w_i + 256 * c;
        const float wr = 0.25f * (bf_lo(__ldg(pr + jj * 257)) + bf_lo(__ldg(pr + jm * 257)));
        const float wi = 0.25f * (bf_lo(__ldg(pi + jj * 257)) - bf_lo(__ldg(pi + jm * 257)));
        st_u2(ws->Wh + c * 2048 + jj, c ? pack_bf16(-wi, wr) : pack_bf16(wr, wi), tag);
        __syncwarp();
        hint_add_if(lane == 0, &ws->cntW[0]);
        mbar_wait(bars + 8 * B_XS, 0);
        const uint32_t t0 = (uint32_t)clock();
        uint4 v;
        do { v = ld_x4(ws->gate + rb * 128 + 4 * lane); spin_guard(t0); } while (__any_sync(0xffffffffu, ((v.x ^ tag) | (v.y ^ tag) | (v.z ^ tag) | (v.w ^ tag)) & 1));
        *(uint4*)(smem + OFF_G + lane * 16) = v;
        __syncwarp();
        mbar_arrive_if(lane < 4, bars + 8 * B_G);
      }
    auto part_load = [&](int i, unsigned ep1) {
      flag_wait(&ws->cntP[32 * (rb * 8 + j) + 8 * i], ep1 * 8u);
      mbar_wait(bars + 8 * (B_PZ + (i == 0)), 0);
      if (i == 2) PROF_EV(26);
      mbar_expect_tx(bars + 8 * (B_HP + i), U);
      bulk_load(sb + (i ? (i - 1) * U : OFF_T), ws->part + (size_t)((rb * 8 + j) * 3 + i) * 1024, U, bars + 8 * (B_HP + i));
    };
    if ((!helper || warp == 15) && elect_one()) {
      if (warp < 14) {
        const int p = warp - 12;
#pragma unroll 1
        for (int i = 4 + p; i < 14; i += 2) asm volatile("prefetch.tensormap [%0];" ::"l"((const char*)&maps + i * 128) : "memory");
#pragma unroll 1
        for (int n = 2; n < 31; n++) {
          const bool table = n == 4 || n >= 29;
          const bool half = n >= 17 && n < 21;
          const int q = n < 4 ? n : n < 17 ? n - 1 : n - 5;
          const CUtensorMap* m = table ? &maps.e : half ? &maps.g32 + p : &maps.g64 + p;
          const int c0 = table ? 0 : half ? f_half : f_full + 64 * (q >> 3);
          const int c1 = table ? (2 * rb + ((n & 1) ^ 1)) * 128 + 64 * p : half ? 128 * (n - 17) : 64 * (q & 7);
          const uint32_t fb = bars + 8 * (B_FA + (n & 3)), dst = sb + OFF_RING + (n & 3) * U + p * 8192;
          if (n < 4) mbar_wait(bars + 8 * (B_FE + n - 2), 0);
          else mbar_wait(bars + 8 * (B_EA + (n & 3)), ((n >> 2) & 1) ^ 1);
          tma2d(dst, m, fb, c0, c1);
          if (p == 0) mbar_expect_tx(fb, U);
        }
        mbar_wait(bars + 8 * (B_PZ + 1), 0);
        part_load(1 + p, ld_x1(&ws->epoch[blockIdx.x * 8]) + 1);
      } else if (warp == 15) {
        const unsigned ep1 = ld_x1(&ws->epoch[blockIdx.x * 8]) + 1;
        flag_wait(&ws->cntX[helper ? 0 : 32 * j], ep1 * 16u);
        PROF_EV(22);
        mbar_expect_tx(bars + 8 * B_HX, U);
        bulk_load(sb + OFF_XB, ws->X + (size_t)(helper ? 128 : kg * 8 + tn) * 8192, U, bars + 8 * B_HX);
        if (!helper) {
          flag_wait(&ws->cntT[32 * j], ep1 * 64u);
          PROF_EV(23);
          mbar_expect_tx(bars + 8 * B_TL, U);
          tma3d(sb + OFF_T, &maps.t, bars + 8 * B_TL, 64 * j, 0, 2 * rb);
          part_load(0, ep1);
          mbar_wait(bars + 8 * (B_HP + 1), 0); mbar_wait(bars + 8 * (B_HP + 2), 0);
          ws->epoch[blockIdx.x * 8] = ep1;
        }
      } else {
#pragma unroll 1
        for (int q = 4; q < 8; q++) xf_load(q);
        mbar_wait(bars + 8 * (B_FE + 2), 0);
        mbar_expect_tx(bars + 8 * B_E0, U);
        tma2d(sb + OFF_XB, &maps.e, bars + 8 * B_E0, 0, 2 * rb * 128);
        tma2d(sb + OFF_XB + 8192, &maps.e, bars + 8 * B_E0, 0, 2 * rb * 128 + 64);
#pragma unroll 1
        for (int h2 = 0; h2 < 2; h2++) {
          const int s0 = 2 * rb + h2, sg = (s0 & ~6) | ((s0 & 2) << 1) | ((s0 & 4) >> 1);
          mbar_wait(bars + 8 * (B_XS + h2), 0);
#pragma unroll 1
          for (int c = 0; c < 2; c++) {
            asm volatile("cp.async.bulk.tensor.4d.global.shared::cta.bulk_group [%0, {%2, %3, %4, %5}], [%1];" ::"l"(&maps.xs),
                         "r"(sb + OFF_XB + h2 * 8192 + c * 4096), "r"(0), "r"(sg), "r"(0), "r"(16 * j + 8 * c) : "memory");
            if (j == 0)
              asm volatile("cp.async.bulk.global.shared::cta.bulk_group [%0], [%1], 256;" ::"l"(ws->X + 128 * 8192 + c * 4096 + sg * 128),
                           "r"(sb + OFF_SP + h2 * 512 + c * 256) : "memory");
            if (SPACE && h2 + c < 2) __nanosleep(SPACE);
          }
        }
        bulk_done_signal(&ws->cntX[32 * j]);
        PROF_EV(20);
        if (rb < 8) asm volatile("cp.async.bulk.prefetch.tensor.2d.L2.global [%0, {%1, %2}];" ::"l"(&maps.g32 + (rb >> 2)), "r"(f_half), "r"(128 * (rb & 3)) : "memory");
        else asm volatile("cp.async.bulk.prefetch.tensor.2d.L2.global [%0, {%1, %2}];" ::"l"(&maps.d224), "r"(64 * (rb - 8)), "r"(224 * j) : "memory");
#pragma unroll 1
        for (int t = 0; t < 8; t++) {
          const int i = t < 3 ? t + 1 : t < 6 ? t - 2 : 0;
          const int col = 64 * (2 * ((q4 + i) & 3) + ((t < 3 || t == 6) ? 1 - rank : rank));
          const uint32_t fb = bars + 8 * (B_FT + (t & 3)), dst = sb + (t & 3) * TB;
          mbar_wait(bars + 8 * (B_ET + (t == 2 ? 3 : t & 3)), t >> 2);
          mbar_expect_tx(fb, TB);
          tma2d(dst, &maps.d224, fb, col, 224 * j);
          if (t < 2) mbar_wait(bars + 8 * (B_ET + t + 1), 0);
          tma2d(dst + 28672, &maps.ft, fb, col, 64 * j);
        }
      }
    }
  }
}

typedef CUresult (*EncodeFn)(CUtensorMap*, CUtensorMapDataType, cuuint32_t, void*, const cuuint64_t*, const cuuint64_t*, const cuuint32_t*,
                             const cuuint32_t*, CUtensorMapInterleave, CUtensorMapSwizzle, CUtensorMapL2promotion, CUtensorMapFloatOOBfill);

static void encode(EncodeFn f, CUtensorMap* m, const void* base, int rank, const cuuint64_t* dims, const cuuint64_t* strides, const cuuint32_t* box,
                   CUtensorMapSwizzle sw) {
  cuuint32_t es[5] = {1, 1, 1, 1, 1};
  f(m, CU_TENSOR_MAP_DATA_TYPE_BFLOAT16, rank, (void*)base, dims, strides, box, es, CU_TENSOR_MAP_INTERLEAVE_NONE, sw,
    CU_TENSOR_MAP_L2_PROMOTION_L2_128B, CU_TENSOR_MAP_FLOAT_OOB_FILL_NONE);
}

extern "C" void kernel_launch(void* const* d_in, const int* in_sizes, int n_in, void* d_out, int out_size) {
  (void)in_sizes; (void)n_in; (void)out_size;
  const __nv_bfloat16* x = (const __nv_bfloat16*)d_in[0];
  const __nv_bfloat16* w_r = (const __nv_bfloat16*)d_in[1];
  const __nv_bfloat16* w_i = (const __nv_bfloat16*)d_in[2];
  const __nv_bfloat16* Wg = (const __nv_bfloat16*)d_in[4];
  const __nv_bfloat16* Wu = (const __nv_bfloat16*)d_in[5];
  const __nv_bfloat16* Wd = (const __nv_bfloat16*)d_in[6];
  const __nv_bfloat16* gw = (const __nv_bfloat16*)d_in[7];

  void* fp = nullptr; cudaDriverEntryPointQueryResult qr;
  cudaGetDriverEntryPoint("cuTensorMapEncodeTiled", &fp, cudaEnableDefault, &qr);
  EncodeFn enc = (EncodeFn)fp;
  void *pFT, *pET, *pDT, *pW;
  cudaGetSymbolAddress(&pDT, g_DT); cudaGetSymbolAddress(&pW, g_work);
  void *pX = ((Work*)pW)->X, *pT = ((Work*)pW)->T;
  cudaGetSymbolAddress(&pFT, g_FT); cudaGetSymbolAddress(&pET, g_ET);

  Maps mp;
  const CUtensorMapSwizzle S128 = CU_TENSOR_MAP_SWIZZLE_128B, S64 = CU_TENSOR_MAP_SWIZZLE_64B;
  { cuuint64_t d[3] = {512, 64, 32}, s[2] = {32768, 1024}; cuuint32_t b[3] = {64, 64, 2}, b2[3] = {64, 16, 1};
    encode(enc, &mp.x, x, 3, d, s, b, S128); encode(enc, &mp.o, d_out, 3, d, s, b2, S128); }
  { cuuint64_t d[2] = {512, 512}, s[1] = {1024}; cuuint32_t b[2] = {64, 64}; encode(enc, &mp.ft, pFT, 2, d, s, b, S128); }
  { cuuint64_t d[4] = {128, 32, 2, 129}, s[3] = {256, 8192, 16384}; cuuint32_t b[4] = {128, 1, 2, 8}; encode(enc, &mp.xs, pX, 4, d, s, b, CU_TENSOR_MAP_SWIZZLE_NONE); }
  { cuuint64_t d[3] = {512, 32, 64}, s[2] = {65536, 1024}; cuuint32_t b[3] = {32, 32, 2}; encode(enc, &mp.ts, pT, 3, d, s, b, S64); }
  { cuuint64_t d[3] = {512, 64, 32}, s[2] = {1024, 65536}; cuuint32_t b[3] = {64, 64, 2}; encode(enc, &mp.t, pT, 3, d, s, b, S128); }
  { cuuint64_t d[2] = {64, 4096}, s[1] = {128}; cuuint32_t b[2] = {64, 64}; encode(enc, &mp.e, pET, 2, d, s, b, S128); }
  { cuuint64_t d[2] = {1792, 512}, s[1] = {3584}; cuuint32_t b[2] = {64, 64}, b2[2] = {32, 128};
    encode(enc, &mp.g64, Wg, 2, d, s, b, S128); encode(enc, &mp.u64, Wu, 2, d, s, b, S128);
    encode(enc, &mp.g32, Wg, 2, d, s, b2, S64); encode(enc, &mp.u32, Wu, 2, d, s, b2, S64); }
  { cuuint64_t d[2] = {512, 1792}, s[1] = {1024}; cuuint32_t b[2] = {64, 224}; encode(enc, &mp.d224, Wd, 2, d, s, b, S128); }
  { cuuint64_t d[4] = {264, 32, 8, 8}, s[3] = {32896, 512, 4112}; cuuint32_t b[4] = {24, 32, 2, 1};
    encode(enc, &mp.wr, w_r, 4, d, s, b, CU_TENSOR_MAP_SWIZZLE_NONE); encode(enc, &mp.wi, w_i, 4, d, s, b, CU_TENSOR_MAP_SWIZZLE_NONE); }

  cudaFuncSetAttribute(fused_kernel, cudaFuncAttributeMaxDynamicSharedMemorySize, SMEM_BYTES);
  fused_kernel<<<NCTA, 512, SMEM_BYTES>>>((Work*)pW, (const uint16_t*)pDT, w_r, w_i, gw, x, (__nv_bfloat16*)d_out, mp);
}
```

```cpp
#include <cuda_runtime.h>
#include <cuda_bf16.h>
#include <cuda.h>
#include <stdint.h>

namespace tbl {
constexpr double PI = 3.14159265358979323846264338327950288;
constexpr double sin_s(double x) { double t = x, s = x; for (int n = 1; n < 12; n++) { t *= -x * x / ((2 * n) * (2 * n + 1)); s += t; } return s; }
constexpr double cos_s(double x) { double t = 1, s = 1; for (int n = 1; n < 12; n++) { t *= -x * x / ((2 * n - 1) * (2 * n)); s += t; } return s; }
constexpr double cos2048(int m) {
  m &= 2047; if (m > 1024) m = 2048 - m;
  bool neg = false; if (m > 512) { m = 1024 - m; neg = true; }
  double v = (m <= 256) ? cos_s(2 * PI * m / 2048) : sin_s(2 * PI * (512 - m) / 2048);
  return neg ? -v : v;
}
constexpr uint16_t to_bf16(double v) {
  if (v == 0) return 0;
  uint16_t s = 0; if (v < 0) { s = 0x8000; v = -v; }
  int e = 0; while (v >= 2) { v /= 2; e++; } while (v < 1) { v *= 2; e--; }
  double m = (v - 1) * 128; int mi = (int)m; double fr = m - mi;
  if (fr > 0.5 || (fr == 0.5 && (mi & 1))) mi++;
  if (mi == 128) { mi = 0; e++; }
  return (uint16_t)(s | ((e + 127) << 7) | mi);
}
struct CosT { uint16_t v[2048]; constexpr CosT() : v() { for (int i = 0; i < 2048; i++) v[i] = to_bf16(cos2048(i)); } };
struct alignas(1024) FT {
  uint16_t v[512 * 512];
  constexpr FT() : v() {
    CosT c;
    for (int r = 0; r < 512; r++) {
      int k = (r >> 4) * 8 + (r & 7), e = (r >> 3) & 1;
      int mul = 4 * k, add = e ? 512 : 0;
      if (k == 0 && e == 1) { mul = 1024; add = 0; }
      for (int d = 0; d < 512; d++) v[r * 512 + d] = c.v[(d * mul + add) & 2047];
    }
  }
};
struct alignas(1024) ET {
  uint16_t v[2048 * 128];
  constexpr ET() : v() {
    CosT c;
    for (int s = 0; s < 2048; s++)
      for (int j = 0; j < 64; j++) {
        const int o = (s & 31) * 8192 + (s >> 5) * 64 + j;
        v[o] = c.v[(s * j) & 2047]; v[o + 4096] = c.v[(s * j + 512) & 2047];
      }
  }
};
struct alignas(1024) DT {
  uint16_t v[64 * 64];
  constexpr DT() : v() {
    CosT c;
    for (int r = 0; r < 64; r++)
      for (int n = 0; n < 64; n++) {
        const int sg = r >> 1, s0 = (sg & ~6) | ((sg & 2) << 1) | ((sg & 4) >> 1), e = r & 1, f = n & 1;
        const int m = 64 * s0 * (n >> 1) + (e == f ? 0 : e ? -512 : 512);
        v[r * 64 + (((n >> 3) ^ (r & 7)) << 3) + (n & 7)] = c.v[m & 2047];
      }
  }
};
}

__device__ constexpr tbl::FT g_FT = tbl::FT();
__device__ constexpr tbl::ET g_ET = tbl::ET();
__device__ constexpr tbl::DT g_DT = tbl::DT();

struct alignas(1024) Work {
  unsigned epoch[132 * 8];
  unsigned cntX[8 * 32], cntT[8 * 32], cntP[128 * 32], cntW[32], cntH[32];
  alignas(16) float gate[16 * 128];
  alignas(16) uint2 Wh[2 * 2048];
  alignas(16) uint2 Ts[32 * 64];
  alignas(1024) uint16_t X[129 * 8192];
  alignas(1024) uint16_t T[32 * 64 * 512];
  alignas(1024) uint4 part[128 * 3 * 1024];
};
__device__ Work g_work;
#define PROF_EV(i) do {} while (0)
#define PROF_CK(i) do {} while (0)

__device__ __forceinline__ uint32_t smem_u32(const void* p) { return (uint32_t)__cvta_generic_to_shared(p); }
__device__ __forceinline__ void mbar_init(uint32_t bar, uint32_t cnt) { asm volatile("mbarrier.init.shared::cta.b64 [%0], %1;" ::"r"(bar), "r"(cnt)); }
__device__ __forceinline__ void mbar_expect_tx(uint32_t bar, uint32_t bytes) { asm volatile("mbarrier.arrive.expect_tx.shared::cta.b64 _, [%0], %1;" ::"r"(bar), "r"(bytes) : "memory"); }
__device__ __forceinline__ void mbar_arrive(uint32_t bar) { asm volatile("mbarrier.arrive.shared::cta.b64 _, [%0];" ::"r"(bar) : "memory"); }
__device__ __forceinline__ bool elect_one() {
  uint32_t p;
  asm volatile("{\n.reg .pred p;\nelect.sync _|p, 0xffffffff;\nselp.u32 %0, 1, 0, p;\n}" : "=r"(p));
  return p;
}
__device__ __forceinline__ void mbar_arrive_if(bool p, uint32_t bar) {
  asm volatile("{\n.reg .pred p;\nsetp.ne.b32 p, %1, 0;\n@p mbarrier.arrive.shared::cta.b64 _, [%0];\n}" ::"r"(bar), "r"((int)p) : "memory");
}
__device__ __forceinline__ void hint_add_if(bool p, unsigned* a) {
  asm volatile("{\n.reg .pred p;\nsetp.ne.b32 p, %1, 0;\n@p red.relaxed.gpu.global.add.u32 [%0], 1;\n}" ::"l"(a), "r"((int)p) : "memory");
}
__device__ __forceinline__ bool mbar_try(uint32_t bar, uint32_t parity) {
  uint32_t ok;
  asm volatile("{\n.reg .pred p;\nmbarrier.test_wait.parity.shared::cta.b64 p, [%1], %2;\nselp.u32 %0, 1, 0, p;\n}" : "=r"(ok) : "r"(bar), "r"(parity) : "memory");
  return ok;
}
__device__ __forceinline__ void mbar_wait(uint32_t bar, uint32_t parity) {
  asm volatile(
      "{\n.reg .pred p;\n.reg .u32 n;\nmov.u32 n, 0;\n"
      "W_LOOP:\nmbarrier.try_wait.parity.shared::cta.b64 p, [%0], %1;\n@p bra W_DONE;\n"
      "add.u32 n, n, 1;\nsetp.lt.u32 p, n, 0x40000;\n@p bra W_LOOP;\ntrap;\nW_DONE:\n}" ::"r"(bar), "r"(parity) : "memory");
}
__device__ __forceinline__ void bulk_load(uint32_t dst, const void* src, uint32_t bytes, uint32_t bar) {
  asm volatile("cp.async.bulk.shared::cluster.global.mbarrier::complete_tx::bytes [%0], [%1], %2, [%3];" ::"r"(dst), "l"(src), "r"(bytes), "r"(bar) : "memory");
}
__device__ __forceinline__ void spin_guard(uint32_t t0) { if ((uint32_t)clock() - t0 > (1u << 30)) __trap(); }
__device__ __forceinline__ float2 ld_x2(const float2* p) { float2 v; asm volatile("ld.relaxed.gpu.global.v2.f32 {%0,%1}, [%2];" : "=f"(v.x), "=f"(v.y) : "l"(p) : "memory"); return v; }
__device__ __forceinline__ void st_u2(uint2* p, uint32_t a, uint32_t b) { asm volatile("st.relaxed.gpu.global.v2.u32 [%0], {%1,%2};" ::"l"(p), "r"(a), "r"(b) : "memory"); }
__device__ __forceinline__ uint32_t ld_x1(const void* p) { uint32_t v; asm volatile("ld.relaxed.gpu.global.u32 %0, [%1];" : "=r"(v) : "l"(p) : "memory"); return v; }
__device__ __forceinline__ uint4 ld_x4(const void* p) { uint4 v; asm volatile("ld.relaxed.gpu.global.v4.u32 {%0,%1,%2,%3}, [%4];" : "=r"(v.x), "=r"(v.y), "=r"(v.z), "=r"(v.w) : "l"(p) : "memory"); return v; }
__device__ __forceinline__ uint32_t mapa(uint32_t a, uint32_t cta) { uint32_t r; asm volatile("mapa.shared::cluster.u32 %0, %1, %2;" : "=r"(r) : "r"(a), "r"(cta)); return r; }
__device__ __forceinline__ void stsm4t(uint32_t a, uint32_t r0, uint32_t r1, uint32_t r2, uint32_t r3) {
  asm volatile("stmatrix.sync.aligned.m8n8.x4.trans.shared.b16 [%0], {%1,%2,%3,%4};" ::"r"(a), "r"(r0), "r"(r1), "r"(r2), "r"(r3) : "memory");
}
__device__ __forceinline__ void hint_add(unsigned* p) { asm volatile("red.relaxed.gpu.global.add.u32 [%0], 1;" ::"l"(p) : "memory"); }
__device__ __forceinline__ void hint_wait(const unsigned* p, unsigned target) {
  const uint32_t t0 = (uint32_t)clock();
  while ((int)(ld_x1(p) - target) < 0) spin_guard(t0);
}
__device__ __forceinline__ void bulk_done_signal(unsigned* p) {
  asm volatile("cp.async.bulk.commit_group;\ncp.async.bulk.wait_group 0;\nfence.proxy.async.global;" ::: "memory");
  hint_add(p);
}
__device__ __forceinline__ void flag_wait(const unsigned* p, unsigned target) {
  hint_wait(p, target);
  asm volatile("fence.proxy.async.global;" ::: "memory");
}
__device__ __forceinline__ void tma2d(uint32_t dst, const CUtensorMap* m, uint32_t bar, int c0, int c1) {
  asm volatile("cp.async.bulk.tensor.2d.shared::cluster.global.mbarrier::complete_tx::bytes [%0], [%1, {%3, %4}], [%2];" ::"r"(dst), "l"(m), "r"(bar), "r"(c0), "r"(c1) : "memory");
}
__device__ __forceinline__ void tma3d(uint32_t dst, const CUtensorMap* m, uint32_t bar, int c0, int c1, int c2) {
  asm volatile("cp.async.bulk.tensor.3d.shared::cluster.global.mbarrier::complete_tx::bytes [%0], [%1, {%3, %4, %5}], [%2];" ::"r"(dst), "l"(m), "r"(bar), "r"(c0), "r"(c1), "r"(c2) : "memory");
}
__device__ __forceinline__ void tma4d(uint32_t dst, const CUtensorMap* m, uint32_t bar, int c0, int c1, int c2, int c3) {
  asm volatile("cp.async.bulk.tensor.4d.shared::cluster.global.mbarrier::complete_tx::bytes [%0], [%1, {%3, %4, %5, %6}], [%2];" ::"r"(dst), "l"(m), "r"(bar), "r"(c0), "r"(c1), "r"(c2), "r"(c3) : "memory");
}
__device__ __forceinline__ void wg_fence() { asm volatile("wgmma.fence.sync.aligned;" ::: "memory"); }
__device__ __forceinline__ void wg_commit() { asm volatile("wgmma.commit_group.sync.aligned;" ::: "memory"); }
template <int N> __device__ __forceinline__ void wg_wait() { asm volatile("wgmma.wait_group.sync.aligned %0;" ::"n"(N) : "memory"); }
template <int O, int N, int NN> __device__ __forceinline__ void fence_regs(float (&d)[NN]) {
#pragma unroll
  for (int i = 0; i < N; i++) asm volatile("" : "+f"(d[O + i])::"memory");
}
__device__ __forceinline__ uint32_t pack_bf16(float lo, float hi) {
  uint32_t r; asm("cvt.rn.bf16x2.f32 %0, %1, %2;" : "=r"(r) : "f"(hi), "f"(lo)); return r;
}
__device__ __forceinline__ uint32_t pack_pin(float lo, float hi) {
  uint32_t r; asm volatile("cvt.rn.bf16x2.f32 %0, %1, %2;" : "=r"(r) : "f"(hi), "f"(lo) : "memory"); return r;
}
__device__ __forceinline__ uint32_t add_bf2(uint32_t a, uint32_t b) { uint32_t r; asm("add.rn.bf16x2 %0, %1, %2;" : "=r"(r) : "r"(a), "r"(b)); return r; }
__device__ __forceinline__ float bf_lo(uint32_t u) { return __uint_as_float(u << 16); }
__device__ __forceinline__ float bf_hi(uint32_t u) { return __uint_as_float(u & 0xffff0000u); }

__device__ __forceinline__ uint64_t d128(uint32_t lo) { uint64_t d; asm("mov.b64 %0, {%1, 0x40000040};" : "=l"(d) : "r"(lo)); return d; }
__device__ __forceinline__ uint64_t d64(uint32_t lo) { uint64_t d; asm("mov.b64 %0, {%1, 0x80000020};" : "=l"(d) : "r"(lo)); return d; }
template<int O,int TB,int ACC,int NN> __device__ __forceinline__ void mma_ss64(float (&d)[NN], uint64_t da, uint64_t db, int sd = 0){
  if constexpr (ACC == 1) asm volatile("wgmma.mma_async.sync.aligned.m64n64k16.f32.bf16.bf16 {%0,%1,%2,%3,%4,%5,%6,%7,%8,%9,%10,%11,%12,%13,%14,%15,%16,%17,%18,%19,%20,%21,%22,%23,%24,%25,%26,%27,%28,%29,%30,%31}, %32, %33, 1, 1, 1, %35, %34;"
   : "+f"(d[O+0]), "+f"(d[O+1]), "+f"(d[O+2]), "+f"(d[O+3]), "+f"(d[O+4]), "+f"(d[O+5]), "+f"(d[O+6]), "+f"(d[O+7]), "+f"(d[O+8]), "+f"(d[O+9]), "+f"(d[O+10]), "+f"(d[O+11]), "+f"(d[O+12]), "+f"(d[O+13]), "+f"(d[O+14]), "+f"(d[O+15]), "+f"(d[O+16]), "+f"(d[O+17]), "+f"(d[O+18]), "+f"(d[O+19]), "+f"(d[O+20]), "+f"(d[O+21]), "+f"(d[O+22]), "+f"(d[O+23]), "+f"(d[O+24]), "+f"(d[O+25]), "+f"(d[O+26]), "+f"(d[O+27]), "+f"(d[O+28]), "+f"(d[O+29]), "+f"(d[O+30]), "+f"(d[O+31])
   : "l"(da), "l"(db), "n"(TB & 1), "n"(TB >> 1));
  else if constexpr (ACC == 0) asm volatile("wgmma.mma_async.sync.aligned.m64n64k16.f32.bf16.bf16 {%0,%1,%2,%3,%4,%5,%6,%7,%8,%9,%10,%11,%12,%13,%14,%15,%16,%17,%18,%19,%20,%21,%22,%23,%24,%25,%26,%27,%28,%29,%30,%31}, %32, %33, 0, 1, 1, %35, %34;"
   : "=f"(d[O+0]), "=f"(d[O+1]), "=f"(d[O+2]), "=f"(d[O+3]), "=f"(d[O+4]), "=f"(d[O+5]), "=f"(d[O+6]), "=f"(d[O+7]), "=f"(d[O+8]), "=f"(d[O+9]), "=f"(d[O+10]), "=f"(d[O+11]), "=f"(d[O+12]), "=f"(d[O+13]), "=f"(d[O+14]), "=f"(d[O+15]), "=f"(d[O+16]), "=f"(d[O+17]), "=f"(d[O+18]), "=f"(d[O+19]), "=f"(d[O+20]), "=f"(d[O+21]), "=f"(d[O+22]), "=f"(d[O+23]), "=f"(d[O+24]), "=f"(d[O+25]), "=f"(d[O+26]), "=f"(d[O+27]), "=f"(d[O+28]), "=f"(d[O+29]), "=f"(d[O+30]), "=f"(d[O+31])
   : "l"(da), "l"(db), "n"(TB & 1), "n"(TB >> 1));
  else asm volatile("{\n.reg .pred p;\nsetp.ne.b32 p, %36, 0;\nwgmma.mma_async.sync.aligned.m64n64k16.f32.bf16.bf16 {%0,%1,%2,%3,%4,%5,%6,%7,%8,%9,%10,%11,%12,%13,%14,%15,%16,%17,%18,%19,%20,%21,%22,%23,%24,%25,%26,%27,%28,%29,%30,%31}, %32, %33, p, 1, 1, %35, %34;\n}"
   : "+f"(d[O+0]), "+f"(d[O+1]), "+f"(d[O+2]), "+f"(d[O+3]), "+f"(d[O+4]), "+f"(d[O+5]), "+f"(d[O+6]), "+f"(d[O+7]), "+f"(d[O+8]), "+f"(d[O+9]), "+f"(d[O+10]), "+f"(d[O+11]), "+f"(d[O+12]), "+f"(d[O+13]), "+f"(d[O+14]), "+f"(d[O+15]), "+f"(d[O+16]), "+f"(d[O+17]), "+f"(d[O+18]), "+f"(d[O+19]), "+f"(d[O+20]), "+f"(d[O+21]), "+f"(d[O+22]), "+f"(d[O+23]), "+f"(d[O+24]), "+f"(d[O+25]), "+f"(d[O+26]), "+f"(d[O+27]), "+f"(d[O+28]), "+f"(d[O+29]), "+f"(d[O+30]), "+f"(d[O+31])
   : "l"(da), "l"(db), "n"(TB & 1), "n"(TB >> 1), "r"(sd));
}
template<int O,int TB,int ACC,int NN> __device__ __forceinline__ void mma_rs64(float (&d)[NN], uint32_t a0, uint32_t a1, uint32_t a2, uint32_t a3, uint64_t db, int sd = 0){
  if constexpr (ACC == 1) asm volatile("wgmma.mma_async.sync.aligned.m64n64k16.f32.bf16.bf16 {%0,%1,%2,%3,%4,%5,%6,%7,%8,%9,%10,%11,%12,%13,%14,%15,%16,%17,%18,%19,%20,%21,%22,%23,%24,%25,%26,%27,%28,%29,%30,%31}, {%32,%33,%34,%35}, %36, 1, 1, 1, %37;"
   : "+f"(d[O+0]), "+f"(d[O+1]), "+f"(d[O+2]), "+f"(d[O+3]), "+f"(d[O+4]), "+f"(d[O+5]), "+f"(d[O+6]), "+f"(d[O+7]), "+f"(d[O+8]), "+f"(d[O+9]), "+f"(d[O+10]), "+f"(d[O+11]), "+f"(d[O+12]), "+f"(d[O+13]), "+f"(d[O+14]), "+f"(d[O+15]), "+f"(d[O+16]), "+f"(d[O+17]), "+f"(d[O+18]), "+f"(d[O+19]), "+f"(d[O+20]), "+f"(d[O+21]), "+f"(d[O+22]), "+f"(d[O+23]), "+f"(d[O+24]), "+f"(d[O+25]), "+f"(d[O+26]), "+f"(d[O+27]), "+f"(d[O+28]), "+f"(d[O+29]), "+f"(d[O+30]), "+f"(d[O+31])
   : "r"(a0), "r"(a1), "r"(a2), "r"(a3), "l"(db), "n"(TB));
  else if constexpr (ACC == 0) asm volatile("wgmma.mma_async.sync.aligned.m64n64k16.f32.bf16.bf16 {%0,%1,%2,%3,%4,%5,%6,%7,%8,%9,%10,%11,%12,%13,%14,%15,%16,%17,%18,%19,%20,%21,%22,%23,%24,%25,%26,%27,%28,%29,%30,%31}, {%32,%33,%34,%35}, %36, 0, 1, 1, %37;"
   : "=f"(d[O+0]), "=f"(d[O+1]), "=f"(d[O+2]), "=f"(d[O+3]), "=f"(d[O+4]), "=f"(d[O+5]), "=f"(d[O+6]), "=f"(d[O+7]), "=f"(d[O+8]), "=f"(d[O+9]), "=f"(d[O+10]), "=f"(d[O+11]), "=f"(d[O+12]), "=f"(d[O+13]), "=f"(d[O+14]), "=f"(d[O+15]), "=f"(d[O+16]), "=f"(d[O+17]), "=f"(d[O+18]), "=f"(d[O+19]), "=f"(d[O+20]), "=f"(d[O+21]), "=f"(d[O+22]), "=f"(d[O+23]), "=f"(d[O+24]), "=f"(d[O+25]), "=f"(d[O+26]), "=f"(d[O+27]), "=f"(d[O+28]), "=f"(d[O+29]), "=f"(d[O+30]), "=f"(d[O+31])
   : "r"(a0), "r"(a1), "r"(a2), "r"(a3), "l"(db), "n"(TB));
  else asm volatile("{\n.reg .pred p;\nsetp.ne.b32 p, %38, 0;\nwgmma.mma_async.sync.aligned.m64n64k16.f32.bf16.bf16 {%0,%1,%2,%3,%4,%5,%6,%7,%8,%9,%10,%11,%12,%13,%14,%15,%16,%17,%18,%19,%20,%21,%22,%23,%24,%25,%26,%27,%28,%29,%30,%31}, {%32,%33,%34,%35}, %36, p, 1, 1, %37;\n}"
   : "+f"(d[O+0]), "+f"(d[O+1]), "+f"(d[O+2]), "+f"(d[O+3]), "+f"(d[O+4]), "+f"(d[O+5]), "+f"(d[O+6]), "+f"(d[O+7]), "+f"(d[O+8]), "+f"(d[O+9]), "+f"(d[O+10]), "+f"(d[O+11]), "+f"(d[O+12]), "+f"(d[O+13]), "+f"(d[O+14]), "+f"(d[O+15]), "+f"(d[O+16]), "+f"(d[O+17]), "+f"(d[O+18]), "+f"(d[O+19]), "+f"(d[O+20]), "+f"(d[O+21]), "+f"(d[O+22]), "+f"(d[O+23]), "+f"(d[O+24]), "+f"(d[O+25]), "+f"(d[O+26]), "+f"(d[O+27]), "+f"(d[O+28]), "+f"(d[O+29]), "+f"(d[O+30]), "+f"(d[O+31])
   : "r"(a0), "r"(a1), "r"(a2), "r"(a3), "l"(db), "n"(TB), "r"(sd));
}
template<int O,int TB,int ACC,int NN> __device__ __forceinline__ void mma_ss128(float (&d)[NN], uint64_t da, uint64_t db, int sd = 0){
  if constexpr (ACC == 1) asm volatile("wgmma.mma_async.sync.aligned.m64n128k16.f32.bf16.bf16 {%0,%1,%2,%3,%4,%5,%6,%7,%8,%9,%10,%11,%12,%13,%14,%15,%16,%17,%18,%19,%20,%21,%22,%23,%24,%25,%26,%27,%28,%29,%30,%31,%32,%33,%34,%35,%36,%37,%38,%39,%40,%41,%42,%43,%44,%45,%46,%47,%48,%49,%50,%51,%52,%53,%54,%55,%56,%57,%58,%59,%60,%61,%62,%63}, %64, %65, 1, 1, 1, %67, %66;"
   : "+f"(d[O+0]), "+f"(d[O+1]), "+f"(d[O+2]), "+f"(d[O+3]), "+f"(d[O+4]), "+f"(d[O+5]), "+f"(d[O+6]), "+f"(d[O+7]), "+f"(d[O+8]), "+f"(d[O+9]), "+f"(d[O+10]), "+f"(d[O+11]), "+f"(d[O+12]), "+f"(d[O+13]), "+f"(d[O+14]), "+f"(d[O+15]), "+f"(d[O+16]), "+f"(d[O+17]), "+f"(d[O+18]), "+f"(d[O+19]), "+f"(d[O+20]), "+f"(d[O+21]), "+f"(d[O+22]), "+f"(d[O+23]), "+f"(d[O+24]), "+f"(d[O+25]), "+f"(d[O+26]), "+f"(d[O+27]), "+f"(d[O+28]), "+f"(d[O+29]), "+f"(d[O+30]), "+f"(d[O+31]), "+f"(d[O+32]), "+f"(d[O+33]), "+f"(d[O+34]), "+f"(d[O+35]), "+f"(d[O+36]), "+f"(d[O+37]), "+f"(d[O+38]), "+f"(d[O+39]), "+f"(d[O+40]), "+f"(d[O+41]), "+f"(d[O+42]), "+f"(d[O+43]), "+f"(d[O+44]), "+f"(d[O+45]), "+f"(d[O+46]), "+f"(d[O+47]), "+f"(d[O+48]), "+f"(d[O+49]), "+f"(d[O+50]), "+f"(d[O+51]), "+f"(d[O+52]), "+f"(d[O+53]), "+f"(d[O+54]), "+f"(d[O+55]), "+f"(d[O+56]), "+f"(d[O+57]), "+f"(d[O+58]), "+f"(d[O+59]), "+f"(d[O+60]), "+f"(d[O+61]), "+f"(d[O+62]), "+f"(d[O+63])
   : "l"(da), "l"(db), "n"(TB & 1), "n"(TB >> 1));
  else if constexpr (ACC == 0) asm volatile("wgmma.mma_async.sync.aligned.m64n128k16.f32.bf16.bf16 {%0,%1,%2,%3,%4,%5,%6,%7,%8,%9,%10,%11,%12,%13,%14,%15,%16,%17,%18,%19,%20,%21,%22,%23,%24,%25,%26,%27,%28,%29,%30,%31,%32,%33,%34,%35,%36,%37,%38,%39,%40,%41,%42,%43,%44,%45,%46,%47,%48,%49,%50,%51,%52,%53,%54,%55,%56,%57,%58,%59,%60,%61,%62,%63}, %64, %65, 0, 1, 1, %67, %66;"
   : "=f"(d[O+0]), "=f"(d[O+1]), "=f"(d[O+2]), "=f"(d[O+3]), "=f"(d[O+4]), "=f"(d[O+5]), "=f"(d[O+6]), "=f"(d[O+7]), "=f"(d[O+8]), "=f"(d[O+9]), "=f"(d[O+10]), "=f"(d[O+11]), "=f"(d[O+12]), "=f"(d[O+13]), "=f"(d[O+14]), "=f"(d[O+15]), "=f"(d[O+16]), "=f"(d[O+17]), "=f"(d[O+18]), "=f"(d[O+19]), "=f"(d[O+20]), "=f"(d[O+21]), "=f"(d[O+22]), "=f"(d[O+23]), "=f"(d[O+24]), "=f"(d[O+25]), "=f"(d[O+26]), "=f"(d[O+27]), "=f"(d[O+28]), "=f"(d[O+29]), "=f"(d[O+30]), "=f"(d[O+31]), "=f"(d[O+32]), "=f"(d[O+33]), "=f"(d[O+34]), "=f"(d[O+35]), "=f"(d[O+36]), "=f"(d[O+37]), "=f"(d[O+38]), "=f"(d[O+39]), "=f"(d[O+40]), "=f"(d[O+41]), "=f"(d[O+42]), "=f"(d[O+43]), "=f"(d[O+44]), "=f"(d[O+45]), "=f"(d[O+46]), "=f"(d[O+47]), "=f"(d[O+48]), "=f"(d[O+49]), "=f"(d[O+50]), "=f"(d[O+51]), "=f"(d[O+52]), "=f"(d[O+53]), "=f"(d[O+54]), "=f"(d[O+55]), "=f"(d[O+56]), "=f"(d[O+57]), "=f"(d[O+58]), "=f"(d[O+59]), "=f"(d[O+60]), "=f"(d[O+61]), "=f"(d[O+62]), "=f"(d[O+63])
   : "l"(da), "l"(db), "n"(TB & 1), "n"(TB >> 1));
  else asm volatile("{\n.reg .pred p;\nsetp.ne.b32 p, %68, 0;\nwgmma.mma_async.sync.aligned.m64n128k16.f32.bf16.bf16 {%0,%1,%2,%3,%4,%5,%6,%7,%8,%9,%10,%11,%12,%13,%14,%15,%16,%17,%18,%19,%20,%21,%22,%23,%24,%25,%26,%27,%28,%29,%30,%31,%32,%33,%34,%35,%36,%37,%38,%39,%40,%41,%42,%43,%44,%45,%46,%47,%48,%49,%50,%51,%52,%53,%54,%55,%56,%57,%58,%59,%60,%61,%62,%63}, %64, %65, p, 1, 1, %67, %66;\n}"
   : "+f"(d[O+0]), "+f"(d[O+1]), "+f"(d[O+2]), "+f"(d[O+3]), "+f"(d[O+4]), "+f"(d[O+5]), "+f"(d[O+6]), "+f"(d[O+7]), "+f"(d[O+8]), "+f"(d[O+9]), "+f"(d[O+10]), "+f"(d[O+11]), "+f"(d[O+12]), "+f"(d[O+13]), "+f"(d[O+14]), "+f"(d[O+15]), "+f"(d[O+16]), "+f"(d[O+17]), "+f"(d[O+18]), "+f"(d[O+19]), "+f"(d[O+20]), "+f"(d[O+21]), "+f"(d[O+22]), "+f"(d[O+23]), "+f"(d[O+24]), "+f"(d[O+25]), "+f"(d[O+26]), "+f"(d[O+27]), "+f"(d[O+28]), "+f"(d[O+29]), "+f"(d[O+30]), "+f"(d[O+31]), "+f"(d[O+32]), "+f"(d[O+33]), "+f"(d[O+34]), "+f"(d[O+35]), "+f"(d[O+36]), "+f"(d[O+37]), "+f"(d[O+38]), "+f"(d[O+39]), "+f"(d[O+40]), "+f"(d[O+41]), "+f"(d[O+42]), "+f"(d[O+43]), "+f"(d[O+44]), "+f"(d[O+45]), "+f"(d[O+46]), "+f"(d[O+47]), "+f"(d[O+48]), "+f"(d[O+49]), "+f"(d[O+50]), "+f"(d[O+51]), "+f"(d[O+52]), "+f"(d[O+53]), "+f"(d[O+54]), "+f"(d[O+55]), "+f"(d[O+56]), "+f"(d[O+57]), "+f"(d[O+58]), "+f"(d[O+59]), "+f"(d[O+60]), "+f"(d[O+61]), "+f"(d[O+62]), "+f"(d[O+63])
   : "l"(da), "l"(db), "n"(TB & 1), "n"(TB >> 1), "r"(sd));
}
template<int O,int TB,int ACC,int NN> __device__ __forceinline__ void mma_rs128(float (&d)[NN], uint32_t a0, uint32_t a1, uint32_t a2, uint32_t a3, uint64_t db, int sd = 0){
  if constexpr (ACC == 1) asm volatile("wgmma.mma_async.sync.aligned.m64n128k16.f32.bf16.bf16 {%0,%1,%2,%3,%4,%5,%6,%7,%8,%9,%10,%11,%12,%13,%14,%15,%16,%17,%18,%19,%20,%21,%22,%23,%24,%25,%26,%27,%28,%29,%30,%31,%32,%33,%34,%35,%36,%37,%38,%39,%40,%41,%42,%43,%44,%45,%46,%47,%48,%49,%50,%51,%52,%53,%54,%55,%56,%57,%58,%59,%60,%61,%62,%63}, {%64,%65,%66,%67}, %68, 1, 1, 1, %69;"
   : "+f"(d[O+0]), "+f"(d[O+1]), "+f"(d[O+2]), "+f"(d[O+3]), "+f"(d[O+4]), "+f"(d[O+5]), "+f"(d[O+6]), "+f"(d[O+7]), "+f"(d[O+8]), "+f"(d[O+9]), "+f"(d[O+10]), "+f"(d[O+11]), "+f"(d[O+12]), "+f"(d[O+13]), "+f"(d[O+14]), "+f"(d[O+15]), "+f"(d[O+16]), "+f"(d[O+17]), "+f"(d[O+18]), "+f"(d[O+19]), "+f"(d[O+20]), "+f"(d[O+21]), "+f"(d[O+22]), "+f"(d[O+23]), "+f"(d[O+24]), "+f"(d[O+25]), "+f"(d[O+26]), "+f"(d[O+27]), "+f"(d[O+28]), "+f"(d[O+29]), "+f"(d[O+30]), "+f"(d[O+31]), "+f"(d[O+32]), "+f"(d[O+33]), "+f"(d[O+34]), "+f"(d[O+35]), "+f"(d[O+36]), "+f"(d[O+37]), "+f"(d[O+38]), "+f"(d[O+39]), "+f"(d[O+40]), "+f"(d[O+41]), "+f"(d[O+42]), "+f"(d[O+43]), "+f"(d[O+44]), "+f"(d[O+45]), "+f"(d[O+46]), "+f"(d[O+47]), "+f"(d[O+48]), "+f"(d[O+49]), "+f"(d[O+50]), "+f"(d[O+51]), "+f"(d[O+52]), "+f"(d[O+53]), "+f"(d[O+54]), "+f"(d[O+55]), "+f"(d[O+56]), "+f"(d[O+57]), "+f"(d[O+58]), "+f"(d[O+59]), "+f"(d[O+60]), "+f"(d[O+61]), "+f"(d[O+62]), "+f"(d[O+63])
   : "r"(a0), "r"(a1), "r"(a2), "r"(a3), "l"(db), "n"(TB));
  else if constexpr (ACC == 0) asm volatile("wgmma.mma_async.sync.aligned.m64n128k16.f32.bf16.bf16 {%0,%1,%2,%3,%4,%5,%6,%7,%8,%9,%10,%11,%12,%13,%14,%15,%16,%17,%18,%19,%20,%21,%22,%23,%24,%25,%26,%27,%28,%29,%30,%31,%32,%33,%34,%35,%36,%37,%38,%39,%40,%41,%42,%43,%44,%45,%46,%47,%48,%49,%50,%51,%52,%53,%54,%55,%56,%57,%58,%59,%60,%61,%62,%63}, {%64,%65,%66,%67}, %68, 0, 1, 1, %69;"
   : "=f"(d[O+0]), "=f"(d[O+1]), "=f"(d[O+2]), "=f"(d[O+3]), "=f"(d[O+4]), "=f"(d[O+5]), "=f"(d[O+6]), "=f"(d[O+7]), "=f"(d[O+8]), "=f"(d[O+9]), "=f"(d[O+10]), "=f"(d[O+11]), "=f"(d[O+12]), "=f"(d[O+13]), "=f"(d[O+14]), "=f"(d[O+15]), "=f"(d[O+16]), "=f"(d[O+17]), "=f"(d[O+18]), "=f"(d[O+19]), "=f"(d[O+20]), "=f"(d[O+21]), "=f"(d[O+22]), "=f"(d[O+23]), "=f"(d[O+24]), "=f"(d[O+25]), "=f"(d[O+26]), "=f"(d[O+27]), "=f"(d[O+28]), "=f"(d[O+29]), "=f"(d[O+30]), "=f"(d[O+31]), "=f"(d[O+32]), "=f"(d[O+33]), "=f"(d[O+34]), "=f"(d[O+35]), "=f"(d[O+36]), "=f"(d[O+37]), "=f"(d[O+38]), "=f"(d[O+39]), "=f"(d[O+40]), "=f"(d[O+41]), "=f"(d[O+42]), "=f"(d[O+43]), "=f"(d[O+44]), "=f"(d[O+45]), "=f"(d[O+46]), "=f"(d[O+47]), "=f"(d[O+48]), "=f"(d[O+49]), "=f"(d[O+50]), "=f"(d[O+51]), "=f"(d[O+52]), "=f"(d[O+53]), "=f"(d[O+54]), "=f"(d[O+55]), "=f"(d[O+56]), "=f"(d[O+57]), "=f"(d[O+58]), "=f"(d[O+59]), "=f"(d[O+60]), "=f"(d[O+61]), "=f"(d[O+62]), "=f"(d[O+63])
   : "r"(a0), "r"(a1), "r"(a2), "r"(a3), "l"(db), "n"(TB));
  else asm volatile("{\n.reg .pred p;\nsetp.ne.b32 p, %70, 0;\nwgmma.mma_async.sync.aligned.m64n128k16.f32.bf16.bf16 {%0,%1,%2,%3,%4,%5,%6,%7,%8,%9,%10,%11,%12,%13,%14,%15,%16,%17,%18,%19,%20,%21,%22,%23,%24,%25,%26,%27,%28,%29,%30,%31,%32,%33,%34,%35,%36,%37,%38,%39,%40,%41,%42,%43,%44,%45,%46,%47,%48,%49,%50,%51,%52,%53,%54,%55,%56,%57,%58,%59,%60,%61,%62,%63}, {%64,%65,%66,%67}, %68, p, 1, 1, %69;\n}"
   : "+f"(d[O+0]), "+f"(d[O+1]), "+f"(d[O+2]), "+f"(d[O+3]), "+f"(d[O+4]), "+f"(d[O+5]), "+f"(d[O+6]), "+f"(d[O+7]), "+f"(d[O+8]), "+f"(d[O+9]), "+f"(d[O+10]), "+f"(d[O+11]), "+f"(d[O+12]), "+f"(d[O+13]), "+f"(d[O+14]), "+f"(d[O+15]), "+f"(d[O+16]), "+f"(d[O+17]), "+f"(d[O+18]), "+f"(d[O+19]), "+f"(d[O+20]), "+f"(d[O+21]), "+f"(d[O+22]), "+f"(d[O+23]), "+f"(d[O+24]), "+f"(d[O+25]), "+f"(d[O+26]), "+f"(d[O+27]), "+f"(d[O+28]), "+f"(d[O+29]), "+f"(d[O+30]), "+f"(d[O+31]), "+f"(d[O+32]), "+f"(d[O+33]), "+f"(d[O+34]), "+f"(d[O+35]), "+f"(d[O+36]), "+f"(d[O+37]), "+f"(d[O+38]), "+f"(d[O+39]), "+f"(d[O+40]), "+f"(d[O+41]), "+f"(d[O+42]), "+f"(d[O+43]), "+f"(d[O+44]), "+f"(d[O+45]), "+f"(d[O+46]), "+f"(d[O+47]), "+f"(d[O+48]), "+f"(d[O+49]), "+f"(d[O+50]), "+f"(d[O+51]), "+f"(d[O+52]), "+f"(d[O+53]), "+f"(d[O+54]), "+f"(d[O+55]), "+f"(d[O+56]), "+f"(d[O+57]), "+f"(d[O+58]), "+f"(d[O+59]), "+f"(d[O+60]), "+f"(d[O+61]), "+f"(d[O+62]), "+f"(d[O+63])
   : "r"(a0), "r"(a1), "r"(a2), "r"(a3), "l"(db), "n"(TB), "r"(sd));
}

#define NEARLY 0
#define XAHEAD 3
#define HEADN 6
#define WBATCH 1
#define WB 8
#define WSLEEP 20
#define XSPREAD 4
#define NOSEND 0
#define MSPLIT 3
#define PFALL 1
#define L2PF 1
#define STAG 0
#define EPF 2
#define XNB 2
#define FNB 0
#define GNB 0
#define TH 4
#define PF0 4
#define FSPLIT 1
#define MGLU 1
#define SPC 2
#define TL 14
#define SPACE 40
#define WPF 1
#define WAFTER 7
#define WPACE 0
#define GATE_AT 4
#define TPACE 40
#define PFMODE 0
#define MAPMODE 1
template <int V> struct IC { static constexpr int value = V; };
struct Maps { CUtensorMap x, ft, g64, u64, e, wr, wi, xs, ts, t, g32, u32, d224; };

constexpr int NCTA = 130;
constexpr int U = 16384;
constexpr int TB = 36864;
constexpr int OFF_RING = 8 * U, OFF_Z = 12 * U, OFF_XB = 12 * U, OFF_T = 13 * U, OFF_D = OFF_T;
constexpr int OFF_BAR = 14 * U, OFF_SP = OFF_BAR + 512, OFF_G = OFF_SP + 1024 + 128;
constexpr int SMEM_BYTES = OFF_G + 512;
constexpr int B_FX = 0, B_FA = 8, B_FT = 12, B_Z = 16, B_W = 24, B_HX = 25, B_TL = 26, B_HP = 27, B_WR = 30, B_E0 = 34;
constexpr int B_EA = 35, B_ET = 39, B_PZ = 43, B_RDY = 45, B_FE = 46;
constexpr int B_T = 50, B_XS = 51, B_G = 53, B_RD0 = 54, NBAR = 55;
__host__ __device__ constexpr int rslot(int n) { return n & 3; }
__host__ __device__ constexpr int rpar(int n) { return (n >> 2) & 1; }

__global__ void __cluster_dims__(2, 1, 1) __launch_bounds__(512, 1)
fused_kernel(Work* __restrict__ ws, const uint16_t* __restrict__ dtab, const __nv_bfloat16* __restrict__ w_r, const __nv_bfloat16* __restrict__ w_i,
             const __nv_bfloat16* __restrict__ gate_w, const __nv_bfloat16* __restrict__ x, __nv_bfloat16* __restrict__ out,
             const __grid_constant__ Maps maps) {
  extern __shared__ __align__(1024) uint8_t smem[];
  if (threadIdx.x < 32 && elect_one()) {
#pragma unroll
    for (int i = 0; i < PF0; i++) asm volatile("prefetch.tensormap [%0];" ::"l"((const char*)&maps + i * 128) : "memory");
  }
  const uint32_t sb = smem_u32(smem);
  const uint32_t bars = sb + OFF_BAR;
  const int tid = threadIdx.x, lane = tid & 31;
  const int warp = __shfl_sync(0xffffffffu, tid >> 5, 0);
  const bool helper = blockIdx.x >= 128;
  const int cl = (blockIdx.x >> 1) & 63, rank = blockIdx.x & 1;
  const int q4 = (cl & 1) | ((cl >> 2) & 2), rb = ((cl >> 1) & 3) | ((cl >> 4) << 2);
  const int j = 2 * q4 + rank;
  const int f_full = 448 * q4 + (rank ? 256 : 0);
  const int f_half = 448 * q4 + (rank ? 224 : 192);
  const int kg = 2 * j + (rb >> 3), tn = rb & 7;

  if (tid == 64) { PROF_EV(0); PROF_CK(40); }
  if (warp < 8) {
    if (!helper && tid < 32) {
      const int r = 16 * j + (tid & 15);
      asm volatile("prefetch.global.L2 [%0];" ::"l"(x + (size_t)(2 * rb + (r >> 6) + 32 * (r & 63)) * 512 + 64 * (tid >> 4)));
    }
    asm volatile("barrier.cluster.arrive.relaxed.aligned;" ::: "memory");
    asm volatile("setmaxnreg.inc.sync.aligned.u32 192;");
    if (!helper) {
      const int wg = warp >> 2, w = warp & 3, g = lane >> 2;
      const bool elect = (tid & 127) == 0;
      float cX[32], cA[64], cB[64], cC[64], ci[64], ct[64];
      const int zero = blockIdx.x >> 16;
      uint32_t h[56], yf[16];
      const uint32_t d0 = (sb & 0x3FFFF) >> 4;
      const uint32_t dK = d0 | (1u << 16), dN = d0 | (512u << 16);
      const uint32_t dX = dK + wg * 512;
      constexpr uint32_t RING = OFF_RING >> 4;
      auto waitA = [&](int n) { mbar_wait(bars + 8 * (B_FA + rslot(n)), rpar(n)); };
      auto freeA = [&](int n) { mbar_arrive_if(elect, bars + 8 * (B_EA + rslot(n))); };
      auto nop = [] {};

      asm volatile("bar.sync 0, 384;" ::: "memory");
#pragma unroll 1
      for (int i = 0; i < 4; i++) {
        const uint64_t dx = d128(dX + i * 2048), df = d128(dK + (OFF_XB >> 4) + (i & 1) * 1024);
        mbar_wait(bars + 8 * (B_FX + 2 * i), 0);
        wg_fence();
        mma_ss64<0, 0, 2>(cX, df, dx, i);
        mma_ss64<0, 0, 1>(cX, df + 2, dx + 2);
        wg_commit(); wg_wait<1>();
        mbar_arrive_if(elect && i, bars + 8 * (B_EA + rslot(i - 1)));
        mma_ss64<0, 0, 1>(cX, df + 4, dx + 4);
        mma_ss64<0, 0, 1>(cX, df + 6, dx + 6);
        if (i == 0 && tid == 0) PROF_EV(1);
        mbar_wait(bars + 8 * (B_FX + 2 * i + 1), 0);
        wg_fence();
#pragma unroll
        for (int k = 0; k < 4; k++) mma_ss64<0, 0, 1>(cX, df + (512 + k * 2), dx + (1024 + k * 2));
        wg_commit();
        waitA(i);
        wg_fence();
        const uint64_t da = d128(dX + i * 1024), db = d128(dN + RING + i * 1024);
        mma_ss128<0, 1, 2>(cA, da, db, i);
        wg_commit(); wg_wait<1>();
        mbar_arrive_if(elect, bars + 8 * (B_FE + i));
#pragma unroll
        for (int k = 1; k < 4; k++) mma_ss128<0, 1, 1>(cA, da + k * 2, db + k * 128);
        wg_commit();
      }
      fence_regs<0, 32>(cX);
#pragma unroll
      for (int e = 0; e < 16; e++) yf[e] = pack_pin(cX[2 * e], cX[2 * e + 1]);
      if (tid == 0) { PROF_EV(2); PROF_CK(42); }
      {
        waitA(4); mbar_wait(bars + 8 * B_E0, 0);
        const uint64_t de = d128(dN + (wg ? RING : OFF_XB >> 4));
        wg_fence();
        mma_rs128<0, 1, 0>(cB, yf[0], yf[1], yf[2], yf[3], de);
        wg_commit();
        wg_wait<1>();
        freeA(3);
#pragma unroll
        for (int k = 1; k < 4; k++) mma_rs128<0, 1, 1>(cB, yf[4 * k], yf[4 * k + 1], yf[4 * k + 2], yf[4 * k + 3], de + k * 128);
        wg_commit();
      }
      bool rel = false;
      auto acquire = [&](int n) {
        rel = elect;
        if (!mbar_try(bars + 8 * (B_FA + rslot(n)), rpar(n))) { wg_wait<0>(); freeA(n - 1); rel = false; waitA(n); }
      };
      auto freeP = [&](int n) { mbar_arrive_if(rel, bars + 8 * (B_EA + rslot(n - 1))); };
      auto ffn_step = [&](auto first, auto split, float (&acc)[64], int n, int kb, auto done, auto work) {
        constexpr int SPLIT = decltype(split)::value;
        acquire(n);
        wg_fence();
        const uint64_t dx = d128(dX + kb * 1024), db = d128(dN + RING + rslot(n) * 1024);
        mma_ss128<0, 1, decltype(first)::value>(acc, dx, db, kb);
#pragma unroll
        for (int k = 1; k < SPLIT; k++) mma_ss128<0, 1, 1>(acc, dx + k * 2, db + k * 128);
        wg_commit();
        work();
        wg_wait<1>();
        freeP(n);
        done();
        if (SPLIT < 4) {
          wg_fence();
#pragma unroll
          for (int k = SPLIT; k < 4; k++) mma_ss128<0, 1, 1>(acc, dx + k * 2, db + k * 128);
          wg_commit();
        }
      };
      {
        const int s0 = 2 * rb + wg, kr = 2 * ((s0 & 1) | ((s0 & 4) >> 1));
        const int m = lane >> 3, r = lane & 7;
        const uint32_t a0 = sb + OFF_XB + wg * 8192 + (((w >> 1) * 8 + (m >> 1)) * 2 + (w & 1)) * 256 + (m & 1) * 128 + ((r ^ (kr + (m & 1))) << 4);
        ffn_step(IC<1>(), IC<4>(), cA, 5, 4, [&] { fence_regs<0, 64>(cB); }, nop);
        asm volatile("bar.sync 5, 256;" ::: "memory");
        auto stage = [&](int i) {
          stsm4t(a0 + i * 1024, pack_bf16(cB[8 * i] - cB[34 + 8 * i], cB[8 * i + 1] - cB[35 + 8 * i]),
                 pack_bf16(cB[32 + 8 * i] + cB[8 * i + 2], cB[33 + 8 * i] + cB[8 * i + 3]),
                 pack_bf16(cB[8 * i + 4] - cB[38 + 8 * i], cB[8 * i + 5] - cB[39 + 8 * i]),
                 pack_bf16(cB[36 + 8 * i] + cB[8 * i + 6], cB[37 + 8 * i] + cB[8 * i + 7]));
          if (j == 0 && w == 0) {
            const uint32_t a1 = r ? sb + OFF_SP + 1024 : sb + OFF_SP + wg * 512 + (m & 1) * 256 + (m >> 1) * 128;
#pragma unroll
            for (int n = 2 * i; n < 2 * i + 2; n++)
              asm volatile("stmatrix.sync.aligned.m8n8.x4.shared.b16 [%0], {%1,%2,%3,%4};" ::"r"(a1 + ((n ^ (kr + (m >> 1)) ^ r) << 4)),
                           "r"(pack_bf16(cB[4 * n], cB[4 * n + 1])), "r"(pack_bf16(cB[4 * n + 2], cB[4 * n + 3])),
                           "r"(pack_bf16(cB[32 + 4 * n], cB[33 + 4 * n])), "r"(pack_bf16(cB[34 + 4 * n], cB[35 + 4 * n])) : "memory");
          }
        };
        auto publish = [&] {
          asm volatile("fence.proxy.async.shared::cta;" ::: "memory");
          __syncwarp();
          mbar_arrive_if(lane == 0, bars + 8 * (B_XS + wg));
          if (tid == 0) PROF_EV(3);
        };
        stage(0);
        ffn_step(IC<1>(), IC<FSPLIT>(), cA, 6, 5, nop, nop);
        stage(1);
        ffn_step(IC<1>(), IC<FSPLIT>(), cA, 7, 6, nop, nop);
        stage(2);
        ffn_step(IC<1>(), IC<2>(), cA, 8, 7, [&] { stage(3); }, nop);
        publish();
      }
      float g0 = 0.f, g1 = 0.f;
      uint32_t tag = 0;
      uint32_t ob[2] = {0, 0};
      auto glu = [&](auto& acc, int half, int ho, int i0, int i1) {
#pragma unroll
        for (int i = i0; i < i1; i++)
          asm volatile("{\n.reg .b32 a, b;\ncvt.rn.relu.bf16x2.f32 a, %2, %1;\ncvt.rn.bf16x2.f32 b, %4, %3;\nmul.rn.bf16x2 a, a, b;\nmul.rn.bf16x2 %0, a, %5;\n}"
                       : "=r"(h[ho + i]) : "f"(acc[2 * i]), "f"(acc[2 * i + 1]), "f"(acc[half + 2 * i]), "f"(acc[half + 1 + 2 * i]), "r"(ob[i & 1]) : "memory");
      };
      ffn_step(IC<2>(), IC<1>(), cB, 9, zero, nop, nop);
#pragma unroll 1
      for (int kb = 1; kb < 8; kb++)
        ffn_step(IC<1>(), IC<FSPLIT>(), cB, 9 + kb, kb, nop, [&] {
          if (kb == 4 + 2 * wg) {
            mbar_wait(bars + 8 * B_G, 0);
            const uint32_t gb0 = *(const uint32_t*)(smem + OFF_G + (wg * 64 + w * 16 + g) * 4), gb1 = *(const uint32_t*)(smem + OFF_G + (wg * 64 + w * 16 + g + 8) * 4);
            tag = gb0 & 1; g0 = __uint_as_float(gb0 & ~1u); g1 = __uint_as_float(gb1 & ~1u);
            ob[0] = pack_bf16(1.0f - g0, 1.0f - g0); ob[1] = pack_bf16(1.0f - g1, 1.0f - g1);
            glu(cA, 32, 0, 0, 16);
          }
        });
      if (tid == 0) { PROF_EV(4); PROF_CK(43); }
      auto m_step = [&](auto first, int i) {
        acquire(17 + i);
        wg_fence();
        const uint64_t dx = d128(dX + i * 2048), dm = d64(dN + RING + rslot(17 + i) * 1024);
        mma_ss64<0, 1, decltype(first)::value>(ct, dx, dm);
#pragma unroll
        for (int k = 1; k < MSPLIT; k++) mma_ss64<0, 1, 1>(ct, dx + ((k >> 2) * 1024 + (k & 3) * 2), dm + k * 64);
        wg_commit();
        wg_wait<1>();
        freeP(17 + i);
        wg_fence();
#pragma unroll
        for (int k = MSPLIT; k < 8; k++) mma_ss64<0, 1, 1>(ct, dx + ((k >> 2) * 1024 + (k & 3) * 2), dm + k * 64);
        wg_commit();
      };
      m_step(IC<0>(), 0);
#pragma unroll 1
      for (int i = 1; i < 5; i++) {
        if (i == 1 + 2 * wg) glu(cB, 32, 16, 0, 16);
        if (i < 4) m_step(IC<1>(), i);
      }
      if (tid == 0) { PROF_EV(5); PROF_CK(44); }
      ffn_step(IC<0>(), IC<1>(), cC, 21, 0, nop, nop);
#pragma unroll 1
      for (int kb = 1; kb < 8; kb++)
        ffn_step(IC<1>(), IC<FSPLIT>(), cC, 21 + kb, kb, [&] { mbar_arrive_if(elect && !(kb & 1), bars + 8 * (B_ET + (kb >> 1) - 1)); }, [&] {
          if (kb == 1 + wg) glu(ct, 16, 48, 0, 8);
        });

      auto twait = [&](uint32_t bar, uint32_t par, int) { mbar_wait(bar, par); };
      const int fo = warp * 128 + lane;
      auto fetch = [&](uint4 (&pv)[4], int z) {
        twait(bars + 8 * (z < 4 ? B_Z + 2 * z + wg : B_HP + z - 4), 0, 8 + z);
        const uint8_t* src = smem + (z < 4 ? OFF_Z - z * U : z == 4 ? OFF_T : (z - 5) * U) + fo * 16;
#pragma unroll
        for (int i = 0; i < 4; i++) pv[i] = *(const uint4*)(src + i * 512);
      };
      auto check = [&](uint4 (&pv)[4], int z) {
#pragma unroll 1
        for (int n = 0; __any_sync(0xffffffffu, ((pv[0].x ^ tag) | (pv[1].x ^ tag) | (pv[2].x ^ tag) | (pv[3].x ^ tag)) & 1); n++) {
#pragma unroll
          for (int i = 0; i < 4; i++) pv[i] = ld_x4(ws->part + (size_t)((rb * 8 + j) * 3 + z - 4) * 1024 + fo + i * 32);
          if (n > (1 << 21)) __trap();
        }
#pragma unroll
        for (int i = 0; i < 4; i++) pv[i].x &= ~1u;
      };
      const uint32_t peerZ = mapa(sb + OFF_Z + fo * 16, rank ^ 1), peerB = mapa(bars + 8 * (B_Z + wg), rank ^ 1);
      auto tile_mma = [&](auto off, int t, int k0, int k1, int init) {
        constexpr int O = decltype(off)::value;
        const uint64_t db = d128(dN + (t & 3) * (TB >> 4)), dw = db + rank * 256, dm = db + (rank ? 0 : 1536);
#pragma unroll
        for (int k = k0; k < k1; k++) {
          if (k == 0) mma_rs64<O, 1, 2>(ct, h[0], h[1], h[2], h[3], dw, init);
          else if (k < 14) mma_rs64<O, 1, 1>(ct, h[4 * k], h[4 * k + 1], h[4 * k + 2], h[4 * k + 3], k < 12 ? dw + k * 128 : dm + (k - 12) * 128);
          else mma_rs64<O, 1, 1>(ct, yf[4 * k - 56], yf[4 * k - 55], yf[4 * k - 54], yf[4 * k - 53], db + k * 128);
        }
      };
      uint4 pv[4] = {};
      auto tile = [&](auto off, int t) {
        constexpr int P = 32 - decltype(off)::value;
        const bool grid = t >= 4 && t < 7, pre = t >= 3 && t != 6;
        const int zo = grid ? t - 4 : t == 7 ? 3 : t - 1, z = t - 3;
        const int owner = rb * 8 + 2 * ((q4 + zo + 1) & 3) + rank;
        uint4* dst = ws->part + (size_t)(owner * 3 + zo) * 1024 + fo;
        const uint32_t src = sb + (z < 4 ? OFF_Z - z * U : OFF_T) + fo * 16;
        twait(bars + 8 * (B_FT + (t & 3)), t >> 2, t);
        wg_fence();
        tile_mma(off, t, 0, TH, zero);
        wg_commit();
        wg_wait<1>();
        mbar_arrive_if(elect && t < 6, bars + 8 * (B_ET + t - 1));
        if (t < 3) twait(bars + 8 * (t == 1 ? B_RD0 : B_RDY), 0, 14 + t);
        fence_regs<P, 32>(ct);
#pragma unroll
        for (int i = 0; i < 4; i++) {
          pv[i].x = (add_bf2(pv[i].x, pack_bf16(ct[P + 8 * i], ct[P + 8 * i + 1])) & ~(uint32_t)grid) | (tag & grid);
          pv[i].y = add_bf2(pv[i].y, pack_bf16(ct[P + 8 * i + 2], ct[P + 8 * i + 3]));
          pv[i].z = add_bf2(pv[i].z, pack_bf16(ct[P + 8 * i + 4], ct[P + 8 * i + 5]));
          pv[i].w = add_bf2(pv[i].w, pack_bf16(ct[P + 8 * i + 6], ct[P + 8 * i + 7]));
        }
        if (grid) {
#pragma unroll
          for (int i = 0; i < 4; i++)
            asm volatile("st.relaxed.gpu.global.v4.u32 [%0], {%1,%2,%3,%4};" ::"l"(dst + i * 32), "r"(pv[i].x), "r"(pv[i].y), "r"(pv[i].z), "r"(pv[i].w) : "memory");
          hint_add_if(lane == 0, &ws->cntP[32 * owner + 8 * zo]);
        }
        auto share = [&](int i) {
          asm volatile("st.async.weak.shared::cluster.mbarrier::complete_tx::bytes.v4.b32 [%0], {%2,%3,%4,%5}, [%1];" ::"r"(peerZ - zo * U + i * 512),
                       "r"(peerB + 16 * zo), "r"(pv[i].x), "r"(pv[i].y), "r"(pv[i].z), "r"(pv[i].w) : "memory");
        };
        if (P == 0 && t == 7) { share(1); share(2); share(3); }
#pragma unroll
        for (int i = 0; i < 4; i++) {
          if (i == 0 ? !grid : t < 4) share(i);
          wg_fence();
          tile_mma(off, t, TH + SPC * i, i < 3 ? TH + SPC * i + SPC : TL, 0);
        }
        wg_commit();
        if (pre) twait(bars + 8 * (z < 4 ? B_Z + 2 * z + wg : B_HP), 0, 8 + z);
        wg_fence();
#pragma unroll
        for (int i = 0; i < 4; i++) {
          asm volatile("{\n.reg .pred p;\nsetp.ne.b32 p, %5, 0;\nmov.b32 %0, 0;\nmov.b32 %1, 0;\nmov.b32 %2, 0;\nmov.b32 %3, 0;\n@p ld.shared.v4.u32 {%0,%1,%2,%3}, [%4];\n}"
                       : "=r"(pv[i].x), "=r"(pv[i].y), "=r"(pv[i].z), "=r"(pv[i].w) : "r"(src + i * 512), "r"((int)pre) : "memory");
          tile_mma(off, t, TL + i, i < 3 ? TL + 1 + i : 18, 0);
        }
        wg_commit();
      };
      asm volatile("barrier.cluster.wait.aligned;" ::: "memory");
      twait(bars + 8 * B_FT, 0, 0);
      wg_fence();
      tile_mma(IC<0>(), 0, 0, 5, zero);
      wg_commit();
      wg_wait<1>();
      mbar_arrive_if(elect, bars + 8 * (B_ET + 3));
      glu(cC, 32, 32, 0, 8);
      waitA(29 + wg);
      wg_fence();
      tile_mma(IC<0>(), 0, 5, 8, 0);
      tile_mma(IC<0>(), 0, 12, 14, 0);
      wg_commit();
      glu(cC, 32, 32, 8, 16);
      if (tid == 0) PROF_EV(6);
      if (tid == 128) PROF_EV(27);
      mbar_wait(bars + 8 * (j == 0 ? B_T : B_TL), 0);
      if (tid == 0) { PROF_EV(7); PROF_CK(45); }
      wg_fence();
      {
        const uint64_t dt = d128(dN + (OFF_T >> 4) + wg * 512), de = d128(dK + RING + (1 + wg) * 1024);
        mma_ss64<0, 1, 0>(ci, de, dt);
        mma_ss64<32, 1, 0>(ci, de + 512, dt);
#pragma unroll
        for (int k = 1; k < 4; k++) {
          mma_ss64<0, 1, 1>(ci, de + k * 2, dt + k * 128);
          mma_ss64<32, 1, 1>(ci, de + (512 + k * 2), dt + k * 128);
        }
        wg_commit();
      }
      tile_mma(IC<0>(), 0, 8, 12, 0);
      wg_commit();
      wg_wait<1>();
      if (elect) asm volatile("mbarrier.arrive.shared::cluster.b64 _, [%0];" ::"r"(mapa(bars + 8 * B_RDY, rank ^ 1)) : "memory");
      mbar_arrive_if(elect, bars + 8 * (B_PZ + 1));
      fence_regs<0, 64>(ci);
#pragma unroll
      for (int i = 0; i < 16; i++) {
        const float gg = ((i & 1) ? g1 : g0) * (2.0f / (2048.0f * 512.0f));
        if (i & 2) yf[i] = pack_pin((ci[2 * i] - ci[28 + 2 * i]) * gg, (ci[2 * i + 1] - ci[29 + 2 * i]) * gg);
        else yf[i] = pack_pin((ci[2 * i] + ci[36 + 2 * i]) * gg, (ci[2 * i + 1] + ci[37 + 2 * i]) * gg);
      }
      wg_fence();
      tile_mma(IC<0>(), 0, 14, 18, 0);
      wg_commit();
      if (tid == 0) PROF_EV(8);
      if (tid == 128) PROF_EV(28);
#pragma unroll 1
      for (int t = 1;; t += 2) {
        tile(IC<32>(), t);
        if (t == 7) break;
        tile(IC<0>(), t + 1);
      }
      if (tid == 0) { PROF_EV(9); PROF_CK(46); }
      if (tid == 128) PROF_EV(29);
      {
        uint4 p1[4], p2[4];
        auto acc4 = [&](uint4 (&d)[4], const uint4 (&a)[4]) {
#pragma unroll
          for (int i = 0; i < 4; i++) { d[i].x = add_bf2(d[i].x, a[i].x); d[i].y = add_bf2(d[i].y, a[i].y); d[i].z = add_bf2(d[i].z, a[i].z); d[i].w = add_bf2(d[i].w, a[i].w); }
        };
        fetch(p1, 5);
        fetch(p2, 3);
        if (tid == 0) PROF_EV(25);
        wg_wait<0>();
        fence_regs<32, 32>(ct);
        check(pv, 4); check(p1, 5);
        acc4(pv, p1); acc4(pv, p2);
#pragma unroll
        for (int i = 0; i < 4; i++) {
          pv[i].x = pack_pin(ct[32 + 8 * i] + bf_lo(pv[i].x), ct[33 + 8 * i] + bf_hi(pv[i].x)); pv[i].y = pack_pin(ct[34 + 8 * i] + bf_lo(pv[i].y), ct[35 + 8 * i] + bf_hi(pv[i].y));
          pv[i].z = pack_pin(ct[36 + 8 * i] + bf_lo(pv[i].z), ct[37 + 8 * i] + bf_hi(pv[i].z)); pv[i].w = pack_pin(ct[38 + 8 * i] + bf_lo(pv[i].w), ct[39 + 8 * i] + bf_hi(pv[i].w));
        }
        if (tid == 0) PROF_EV(14);
        fetch(p2, 6);
        if (tid == 0) PROF_EV(24);
        check(p2, 6);
        acc4(pv, p2);
        const uint32_t stg = sb + OFF_T + warp * 2048;
        const int mr = (lane & 7) + ((lane >> 3) & 1) * 8, mc = lane >> 4;
#pragma unroll
        for (int i = 0; i < 4; i++)
          asm volatile("stmatrix.sync.aligned.m8n8.x4.shared.b16 [%0], {%1,%2,%3,%4};" ::"r"(stg + mr * 128 + (((2 * i + mc) ^ (mr & 7)) << 4)), "r"(pv[i].x),
                       "r"(pv[i].y), "r"(pv[i].z), "r"(pv[i].w) : "memory");
        __syncwarp();
#pragma unroll
        for (int i = 0; i < 4; i++) {
          const int r = 4 * i + (lane >> 3), c = lane & 7;
          const uint4 v = *(const uint4*)(smem + OFF_T + warp * 2048 + r * 128 + ((c ^ (r & 7)) << 4));
          *(uint4*)(out + (size_t)(2 * rb + wg + 32 * (16 * w + r)) * 512 + 64 * j + 8 * c) = v;
        }
      }
      if (tid == 0) { PROF_EV(15); PROF_CK(41); }
      if (tid == 128) PROF_EV(30);
    }
  } else if (warp < 12) {
    asm volatile("setmaxnreg.dec.sync.aligned.u32 104;");
    asm volatile("barrier.cluster.arrive.relaxed.aligned;" ::: "memory");
    const int t = tid - 256, w = warp - 8;
    const uint32_t ep = ld_x1(&ws->epoch[blockIdx.x * 8]);
    const uint32_t tag = (ep + 1) & 1;
    auto w_issue = [&](const CUtensorMap* m) {

      if (elect_one()) { mbar_expect_tx(bars + 8 * (B_WR + w), 3072); tma4d(sb + OFF_T + w * 3072, m, bars + 8 * (B_WR + w), 16 * kg, 0, 2 * w, tn); }

          __syncwarp();
    };
    auto gate_rows = [&] {
      const int r = 16 * j + 4 * w + (lane >> 3);
      const uint4* pg = (const uint4*)gate_w + (lane & 7);
      {
        float a = 0.f;
        asm volatile("bar.sync 4, 256;" ::: "memory");
#pragma unroll 1
        for (int hf = 0; hf < 2; hf++) {
          uint4 v[4], u[4];
#pragma unroll
          for (int kb = 0; kb < 4; kb++) v[kb] = __ldg(pg + (4 * hf + kb) * 8);
          mbar_wait(bars + 8 * (B_FE + 1 + 2 * hf), 0);
          if (hf) w_issue(&maps.wr);
#pragma unroll
          for (int kb = 0; kb < 4; kb++) u[kb] = *(const uint4*)(smem + (4 * hf + kb) * U + r * 128 + (((lane ^ r) & 7) << 4));
#pragma unroll
          for (int kb = 0; kb < 4; kb++) {
            const uint32_t uu[4] = {u[kb].x, u[kb].y, u[kb].z, u[kb].w}, vv[4] = {v[kb].x, v[kb].y, v[kb].z, v[kb].w};
#pragma unroll
            for (int e = 0; e < 4; e++) {
              uint32_t pr;
              asm("mul.rn.bf16x2 %0, %1, %2;" : "=r"(pr) : "r"(uu[e]), "r"(vv[e]));
              a += bf_lo(pr) + bf_hi(pr);
            }
          }
        }
#pragma unroll
        for (int o = 4; o; o >>= 1) a += __shfl_xor_sync(0xffffffffu, a, o);
        if ((lane & 7) == 0)
          asm volatile("st.relaxed.gpu.global.u32 [%0], %1;" ::"l"(ws->gate + rb * 128 + r),
                       "r"(pack_bf16(0.f, __fdividef(1.0f, 1.0f + __expf(-bf_lo(pack_bf16(a, 0.f))))) | tag) : "memory");
        if (t == 0) PROF_EV(18);
      }
    };
    {
      const int g = lane >> 2, q = lane & 3;
      uint32_t wf[32];
      if (!helper) {
        gate_rows();
        const uint32_t wa = sb + OFF_T + w * (3072 + 4) + q * 48 + g * 2;
#pragma unroll 1
        for (int ri = 0; ri < 2; ri++) {
          mbar_wait(bars + 8 * (B_WR + w), ri);
#pragma unroll
          for (int n2 = 0; n2 < 32 / WB; n2++) {
            uint32_t v[WB];
#pragma unroll
            for (int i = 0; i < WB; i++) {
              const int e = n2 * WB + i;
              asm volatile("ld.shared.u16 %0, [%1];" : "=r"(v[i]) : "r"(wa + ((e >> 1) & 7) * 192 + (e & 1) * (1536 + 2) + (e >> 4) * 16) : "memory");
            }
#pragma unroll
            for (int i = 0; i < WB; i++) wf[n2 * WB + i] = __byte_perm(wf[n2 * WB + i], v[i], 0x5432);
            if (WSLEEP) { asm volatile("nanosleep.u32 %0;" ::"r"(WSLEEP + (v[WB - 1] >> 16)) : "memory"); }
          }
          __syncwarp();
          if (ri == 0) w_issue(&maps.wi);
        }
        asm volatile("bar.sync 1, 128;" ::: "memory");
        if (t == 0) PROF_EV(11);
      } else {
        asm volatile("bar.sync 4, 256;" ::: "memory");
        hint_wait(&ws->cntW[0], (ep + 1) * 128u);
        const uint32_t t0 = (uint32_t)clock();
#pragma unroll 1
        for (;;) {
          uint32_t bad = 0;
#pragma unroll
          for (int i = 0; i < 32; i++) {
            const float2 v = ld_x2((const float2*)ws->Wh + (i >> 4) * 2048 + 16 * w + g + 8 * (i & 1) + 64 * q + ((i >> 1) & 7) * 256);
            wf[i] = __float_as_uint(v.x); bad |= __float_as_uint(v.y) ^ tag;
          }
          if (!__any_sync(0xffffffffu, bad & 1)) break;
          spin_guard(t0);
        }
        if (t == 0) PROF_EV(11);
      }
      if (w == 0 && elect_one()) { mbar_expect_tx(bars + 8 * B_W, 8192); bulk_load(sb + OFF_D, dtab, 8192, bars + 8 * B_W); }
      asm volatile("barrier.cluster.wait.aligned;" ::: "memory");
      mbar_wait(bars + 8 * B_W, 0);
      mbar_wait(bars + 8 * B_HX, 0);
      if (t == 0) PROF_EV(12);
      const uint32_t dd = (sb & 0x3FFFF) >> 4;
      const uint64_t dF = d128((dd + (OFF_D >> 4)) | (512u << 16)), dI = d128((dd + (OFF_D >> 4)) | (1u << 16)), dA = d128((dd + (OFF_XB >> 4)) | (512u << 16));
      float az[32];
      const int zero = blockIdx.x >> 16;
      uint32_t pf[32];
#pragma unroll
      for (int mt = 0; mt < 2; mt++) {
        wg_fence();
        if (mt == 0) mma_ss64<0, 3, 0>(az, dA, dF);
        else mma_ss64<0, 3, 2>(az, dA + 512, dF, zero);
#pragma unroll
        for (int k = 1; k < 4; k++) mma_ss64<0, 3, 1>(az, dA + (mt * 512 + k * 128), dF + k * 128);
        wg_commit();
        wg_wait<0>();
        fence_regs<0, 32>(az);
#pragma unroll
        for (int i = 0; i < 16; i++) {
          const float wr = bf_lo(wf[16 * mt + i]), wi = bf_hi(wf[16 * mt + i]);
          pf[16 * mt + i] = pack_pin(fmaf(az[2 * i], wr, -az[2 * i + 1] * wi), fmaf(az[2 * i], wi, az[2 * i + 1] * wr));
        }
      }
      if (t == 0) PROF_EV(16);
      {
        const int m = lane >> 3, r = lane & 7;
        const int sl = 2 * (m >> 1) + ((r >> 1) & 1) + 4 * (r >> 2);
        const uint32_t a0 = sb + OFF_XB + (2 * w + (m & 1)) * 2048 + sl * 64;
        uint32_t pk[16];
#pragma unroll
        for (int mt = 0; mt < 3; mt++) {
          if (mt < 2) {
            wg_fence();
            mma_rs64<0, 0, 2>(az, pf[16 * mt], pf[16 * mt + 1], pf[16 * mt + 2], pf[16 * mt + 3], dI, mt ? (int)helper : zero);
#pragma unroll
            for (int k = 1; k < 4; k++) mma_rs64<0, 0, 1>(az, pf[16 * mt + 4 * k], pf[16 * mt + 4 * k + 1], pf[16 * mt + 4 * k + 2], pf[16 * mt + 4 * k + 3], dI + k * 2);
            wg_commit();
          }
          if (mt > 0 && !helper) {
#pragma unroll
            for (int i = 0; i < 4; i++) stsm4t(a0 + ((((mt - 1) * 2 + (r & 1)) ^ (sl >> 1)) << 4) + i * 512, pk[4 * i], pk[4 * i + 1], pk[4 * i + 2], pk[4 * i + 3]);
          }
          if (mt < 2) {
            wg_wait<0>();
            fence_regs<0, 32>(az);
#pragma unroll
            for (int i = 0; i < 16; i++) pk[i] = pack_pin(az[2 * i], az[2 * i + 1]);
          }
        }
      }
      if (helper) {
#pragma unroll
        for (int i = 0; i < 16; i++) {
          const int n = i >> 1, s0 = 8 * (n >> 1) + 2 * (n & 1) + (q & 1) + 4 * (q >> 1);
          if ((n & 1) == (int)(blockIdx.x & 1)) st_u2(ws->Ts + s0 * 64 + 16 * w + g + 8 * (i & 1), pack_bf16(az[2 * i], az[2 * i + 1]), tag);
        }
        __syncwarp();
        hint_add_if(lane == 0, &ws->cntH[0]);
        if (t == 0) { ws->epoch[blockIdx.x * 8] = ep + 1; PROF_EV(13); }
      } else {
        asm volatile("fence.proxy.async.shared::cta;" ::: "memory");
        __syncwarp();
        if (elect_one()) {
          if (t == 0) PROF_EV(17);
          if (SPACE) __nanosleep(SPACE * w);
          asm volatile("cp.async.bulk.tensor.3d.global.shared::cta.bulk_group [%0, {%2, %3, %4}], [%1];" ::"l"(&maps.ts), "r"(sb + OFF_XB + w * 4096),
                       "r"(32 * kg), "r"(0), "r"(8 * tn + 2 * w) : "memory");
          bulk_done_signal(&ws->cntT[32 * j]);
          asm volatile("mbarrier.arrive.shared::cluster.b64 _, [%0];" ::"r"(mapa(bars + 8 * B_RD0, rank ^ 1)) : "memory");
          if (t == 96) PROF_EV(13);
        }
        __syncwarp();
        if (j == 0) {
          hint_wait(&ws->cntH[0], (ep + 1) * 8u);
          const uint32_t t0 = (uint32_t)clock();
          float2 v;
          do { v = ld_x2((const float2*)ws->Ts + 2 * rb * 64 + t); spin_guard(t0); } while (__any_sync(0xffffffffu, (__float_as_uint(v.y) ^ tag) & 1));
          mbar_wait(bars + 8 * B_TL, 0);
          const uint32_t u = __float_as_uint(v.x);
          *(uint16_t*)(smem + OFF_T + t * 128 + ((t & 7) << 4)) = (uint16_t)u;
          *(uint16_t*)(smem + OFF_T + t * 128 + (((t & 7) ^ 1) << 4)) = (uint16_t)(u >> 16);
          asm volatile("fence.proxy.async.shared::cta;" ::: "memory");
          __syncwarp();
          mbar_arrive_if(lane == 0, bars + 8 * B_T);
        }
      }
    }
  } else {
    asm volatile("setmaxnreg.dec.sync.aligned.u32 24;");
    auto xf_load = [&](int q) {
      const uint32_t fb = bars + 8 * (B_FX + q);
      mbar_expect_tx(fb, U + 8192);
      tma3d(sb + q * U, &maps.x, fb, 64 * q, 0, 2 * rb);
      if (q >= 4) mbar_wait(bars + 8 * (B_FE + ((q - 4) >> 1)), 0);
      tma2d(sb + OFF_XB + (q & 3) * 8192, &maps.ft, fb, 64 * q, 64 * j);
    };
    if (elect_one()) {
      if (warp == 14) {
#pragma unroll
        for (int i = 0; i < B_FT; i++) mbar_init(bars + 8 * i, 1);
        asm volatile("fence.mbarrier_init.release.cluster;" ::: "memory");
        if (!helper) {
#pragma unroll 1
          for (int n = 0; n < 2; n++) {
            const uint32_t fb = bars + 8 * (B_FA + n);
            xf_load(2 * n); xf_load(2 * n + 1);
            mbar_expect_tx(fb, U);
            tma2d(sb + OFF_RING + n * U, &maps.g64, fb, f_full, 64 * n);
            tma2d(sb + OFF_RING + n * U + 8192, &maps.u64, fb, f_full, 64 * n);
          }
        }
      } else if (warp == 15) {
#pragma unroll
        for (int i = B_FT; i < NBAR; i++) mbar_init(bars + 8 * i, i < B_EA ? 1 : i < B_T ? 2 : 4);
#pragma unroll
        for (int i = 0; i < 8; i++) mbar_expect_tx(bars + 8 * (B_Z + i), U / 2);
        asm volatile("fence.mbarrier_init.release.cluster;" ::: "memory");
        asm volatile("fence.proxy.async.shared::cta;" ::: "memory");
      }
    }
    __syncwarp();
    asm volatile("bar.arrive 0, 384;" ::: "memory");
    asm volatile("bar.arrive 4, 256;" ::: "memory");
    __syncwarp();
    asm volatile("barrier.cluster.arrive.relaxed.aligned;" ::: "memory");
    asm volatile("bar.sync 3, 128;" ::: "memory");
    if (warp == 15 && !helper) {
        mbar_wait(bars + 8 * B_FE, 0);
        const uint32_t tag = (ld_x1(&ws->epoch[blockIdx.x * 8]) + 1) & 1;
        const int c = lane >> 4, jj = 16 * blockIdx.x + (lane & 15), jm = (2048 - jj) & 2047;
        const unsigned short* pr = (const unsigned short*)w_r + 256 * c;
        const unsigned short* pi = (const unsigned short*)w_i + 256 * c;
        const float wr = 0.25f * (bf_lo(__ldg(pr + jj * 257)) + bf_lo(__ldg(pr + jm * 257)));
        const float wi = 0.25f * (bf_lo(__ldg(pi + jj * 257)) - bf_lo(__ldg(pi + jm * 257)));
        st_u2(ws->Wh + c * 2048 + jj, c ? pack_bf16(-wi, wr) : pack_bf16(wr, wi), tag);
        __syncwarp();
        hint_add_if(lane == 0, &ws->cntW[0]);
        mbar_wait(bars + 8 * B_XS, 0);
        const uint32_t t0 = (uint32_t)clock();
        uint4 v;
        do { v = ld_x4(ws->gate + rb * 128 + 4 * lane); spin_guard(t0); } while (__any_sync(0xffffffffu, ((v.x ^ tag) | (v.y ^ tag) | (v.z ^ tag) | (v.w ^ tag)) & 1));
        *(uint4*)(smem + OFF_G + lane * 16) = v;
        __syncwarp();
        mbar_arrive_if(lane < 4, bars + 8 * B_G);
      }
    auto part_load = [&](int i, unsigned ep1) {
      flag_wait(&ws->cntP[32 * (rb * 8 + j) + 8 * i], ep1 * 8u);
      mbar_wait(bars + 8 * (B_PZ + (i == 0)), 0);
      if (i == 2) PROF_EV(26);
      mbar_expect_tx(bars + 8 * (B_HP + i), U);
      bulk_load(sb + (i ? (i - 1) * U : OFF_T), ws->part + (size_t)((rb * 8 + j) * 3 + i) * 1024, U, bars + 8 * (B_HP + i));
    };
    if ((!helper || warp == 15) && elect_one()) {
      if (warp < 14) {
        const int p = warp - 12;
#pragma unroll 1
        for (int i = 4 + p; i < 13; i += 2) asm volatile("prefetch.tensormap [%0];" ::"l"((const char*)&maps + i * 128) : "memory");
#pragma unroll 1
        for (int n = 2; n < 31; n++) {
          const bool table = n == 4 || n >= 29;
          const bool half = n >= 17 && n < 21;
          const int q = n < 4 ? n : n < 17 ? n - 1 : n - 5;
          const CUtensorMap* m = table ? &maps.e : half ? &maps.g32 + p : &maps.g64 + p;
          const int c0 = table ? 0 : half ? f_half : f_full + 64 * (q >> 3);
          const int c1 = table ? (2 * rb + ((n & 1) ^ 1)) * 128 + 64 * p : half ? 128 * (n - 17) : 64 * (q & 7);
          const uint32_t fb = bars + 8 * (B_FA + (n & 3)), dst = sb + OFF_RING + (n & 3) * U + p * 8192;
          if (n < 4) mbar_wait(bars + 8 * (B_FE + n - 2), 0);
          else mbar_wait(bars + 8 * (B_EA + (n & 3)), ((n >> 2) & 1) ^ 1);
          tma2d(dst, m, fb, c0, c1);
          if (p == 0) mbar_expect_tx(fb, U);
        }
        mbar_wait(bars + 8 * (B_PZ + 1), 0);
        part_load(1 + p, ld_x1(&ws->epoch[blockIdx.x * 8]) + 1);
      } else if (warp == 15) {
        const unsigned ep1 = ld_x1(&ws->epoch[blockIdx.x * 8]) + 1;
        flag_wait(&ws->cntX[helper ? 0 : 32 * j], ep1 * 16u);
        PROF_EV(22);
        mbar_expect_tx(bars + 8 * B_HX, U);
        bulk_load(sb + OFF_XB, ws->X + (size_t)(helper ? 128 : kg * 8 + tn) * 8192, U, bars + 8 * B_HX);
        if (!helper) {
          flag_wait(&ws->cntT[32 * j], ep1 * 64u);
          PROF_EV(23);
          mbar_expect_tx(bars + 8 * B_TL, U);
          tma3d(sb + OFF_T, &maps.t, bars + 8 * B_TL, 64 * j, 0, 2 * rb);
          part_load(0, ep1);
          mbar_wait(bars + 8 * (B_HP + 1), 0); mbar_wait(bars + 8 * (B_HP + 2), 0);
          ws->epoch[blockIdx.x * 8] = ep1;
        }
      } else {
#pragma unroll 1
        for (int q = 4; q < 8; q++) xf_load(q);
        mbar_wait(bars + 8 * (B_FE + 2), 0);
        mbar_expect_tx(bars + 8 * B_E0, U);
        tma2d(sb + OFF_XB, &maps.e, bars + 8 * B_E0, 0, 2 * rb * 128);
        tma2d(sb + OFF_XB + 8192, &maps.e, bars + 8 * B_E0, 0, 2 * rb * 128 + 64);
#pragma unroll 1
        for (int h2 = 0; h2 < 2; h2++) {
          const int s0 = 2 * rb + h2, sg = (s0 & ~6) | ((s0 & 2) << 1) | ((s0 & 4) >> 1);
          mbar_wait(bars + 8 * (B_XS + h2), 0);
#pragma unroll 1
          for (int c = 0; c < 2; c++) {
            asm volatile("cp.async.bulk.tensor.4d.global.shared::cta.bulk_group [%0, {%2, %3, %4, %5}], [%1];" ::"l"(&maps.xs),
                         "r"(sb + OFF_XB + h2 * 8192 + c * 4096), "r"(0), "r"(sg), "r"(0), "r"(16 * j + 8 * c) : "memory");
            if (j == 0)
              asm volatile("cp.async.bulk.global.shared::cta.bulk_group [%0], [%1], 256;" ::"l"(ws->X + 128 * 8192 + c * 4096 + sg * 128),
                           "r"(sb + OFF_SP + h2 * 512 + c * 256) : "memory");
            if (SPACE && h2 + c < 2) __nanosleep(SPACE);
          }
        }
        bulk_done_signal(&ws->cntX[32 * j]);
        PROF_EV(20);
        if (rb < 8) asm volatile("cp.async.bulk.prefetch.tensor.2d.L2.global [%0, {%1, %2}];" ::"l"(&maps.g32 + (rb >> 2)), "r"(f_half), "r"(128 * (rb & 3)) : "memory");
        else asm volatile("cp.async.bulk.prefetch.tensor.2d.L2.global [%0, {%1, %2}];" ::"l"(&maps.d224), "r"(64 * (rb - 8)), "r"(224 * j) : "memory");
#pragma unroll 1
        for (int t = 0; t < 8; t++) {
          const int i = t < 3 ? t + 1 : t < 6 ? t - 2 : 0;
          const int col = 64 * (2 * ((q4 + i) & 3) + ((t < 3 || t == 6) ? 1 - rank : rank));
          const uint32_t fb = bars + 8 * (B_FT + (t & 3)), dst = sb + (t & 3) * TB;
          mbar_wait(bars + 8 * (B_ET + (t == 2 ? 3 : t & 3)), t >> 2);
          mbar_expect_tx(fb, TB);
          tma2d(dst, &maps.d224, fb, col, 224 * j);
          if (t < 2) mbar_wait(bars + 8 * (B_ET + t + 1), 0);
          tma2d(dst + 28672, &maps.ft, fb, col, 64 * j);
        }
      }
    }
  }
}

typedef CUresult (*EncodeFn)(CUtensorMap*, CUtensorMapDataType, cuuint32_t, void*, const cuuint64_t*, const cuuint64_t*, const cuuint32_t*,
                             const cuuint32_t*, CUtensorMapInterleave, CUtensorMapSwizzle, CUtensorMapL2promotion, CUtensorMapFloatOOBfill);

static void encode(EncodeFn f, CUtensorMap* m, const void* base, int rank, const cuuint64_t* dims, const cuuint64_t* strides, const cuuint32_t* box,
                   CUtensorMapSwizzle sw) {
  cuuint32_t es[5] = {1, 1, 1, 1, 1};
  f(m, CU_TENSOR_MAP_DATA_TYPE_BFLOAT16, rank, (void*)base, dims, strides, box, es, CU_TENSOR_MAP_INTERLEAVE_NONE, sw,
    CU_TENSOR_MAP_L2_PROMOTION_L2_128B, CU_TENSOR_MAP_FLOAT_OOB_FILL_NONE);
}

extern "C" void kernel_launch(void* const* d_in, const int* in_sizes, int n_in, void* d_out, int out_size) {
  (void)in_sizes; (void)n_in; (void)out_size;
  const __nv_bfloat16* x = (const __nv_bfloat16*)d_in[0];
  const __nv_bfloat16* w_r = (const __nv_bfloat16*)d_in[1];
  const __nv_bfloat16* w_i = (const __nv_bfloat16*)d_in[2];
  const __nv_bfloat16* Wg = (const __nv_bfloat16*)d_in[4];
  const __nv_bfloat16* Wu = (const __nv_bfloat16*)d_in[5];
  const __nv_bfloat16* Wd = (const __nv_bfloat16*)d_in[6];
  const __nv_bfloat16* gw = (const __nv_bfloat16*)d_in[7];

  void* fp = nullptr; cudaDriverEntryPointQueryResult qr;
  cudaGetDriverEntryPoint("cuTensorMapEncodeTiled", &fp, cudaEnableDefault, &qr);
  EncodeFn enc = (EncodeFn)fp;
  void *pFT, *pET, *pDT, *pW;
  cudaGetSymbolAddress(&pDT, g_DT); cudaGetSymbolAddress(&pW, g_work);
  void *pX = ((Work*)pW)->X, *pT = ((Work*)pW)->T;
  cudaGetSymbolAddress(&pFT, g_FT); cudaGetSymbolAddress(&pET, g_ET);

  Maps mp;
  const CUtensorMapSwizzle S128 = CU_TENSOR_MAP_SWIZZLE_128B, S64 = CU_TENSOR_MAP_SWIZZLE_64B;
  { cuuint64_t d[3] = {512, 64, 32}, s[2] = {32768, 1024}; cuuint32_t b[3] = {64, 64, 2}; encode(enc, &mp.x, x, 3, d, s, b, S128); }
  { cuuint64_t d[2] = {512, 512}, s[1] = {1024}; cuuint32_t b[2] = {64, 64}; encode(enc, &mp.ft, pFT, 2, d, s, b, S128); }
  { cuuint64_t d[4] = {128, 32, 2, 129}, s[3] = {256, 8192, 16384}; cuuint32_t b[4] = {128, 1, 2, 8}; encode(enc, &mp.xs, pX, 4, d, s, b, CU_TENSOR_MAP_SWIZZLE_NONE); }
  { cuuint64_t d[3] = {512, 32, 64}, s[2] = {65536, 1024}; cuuint32_t b[3] = {32, 32, 2}; encode(enc, &mp.ts, pT, 3, d, s, b, S64); }
  { cuuint64_t d[3] = {512, 64, 32}, s[2] = {1024, 65536}; cuuint32_t b[3] = {64, 64, 2}; encode(enc, &mp.t, pT, 3, d, s, b, S128); }
  { cuuint64_t d[2] = {64, 4096}, s[1] = {128}; cuuint32_t b[2] = {64, 64}; encode(enc, &mp.e, pET, 2, d, s, b, S128); }
  { cuuint64_t d[2] = {1792, 512}, s[1] = {3584}; cuuint32_t b[2] = {64, 64}, b2[2] = {32, 128};
    encode(enc, &mp.g64, Wg, 2, d, s, b, S128); encode(enc, &mp.u64, Wu, 2, d, s, b, S128);
    encode(enc, &mp.g32, Wg, 2, d, s, b2, S64); encode(enc, &mp.u32, Wu, 2, d, s, b2, S64); }
  { cuuint64_t d[2] = {512, 1792}, s[1] = {1024}; cuuint32_t b[2] = {64, 224}; encode(enc, &mp.d224, Wd, 2, d, s, b, S128); }
  { cuuint64_t d[4] = {264, 32, 8, 8}, s[3] = {32896, 512, 4112}; cuuint32_t b[4] = {24, 32, 2, 1};
    encode(enc, &mp.wr, w_r, 4, d, s, b, CU_TENSOR_MAP_SWIZZLE_NONE); encode(enc, &mp.wi, w_i, 4, d, s, b, CU_TENSOR_MAP_SWIZZLE_NONE); }

  cudaFuncSetAttribute(fused_kernel, cudaFuncAttributeMaxDynamicSharedMemorySize, SMEM_BYTES);
  fused_kernel<<<NCTA, 512, SMEM_BYTES>>>((Work*)pW, (const uint16_t*)pDT, w_r, w_i, gw, x, (__nv_bfloat16*)d_out, mp);
}
```

```cpp
#include <cuda_runtime.h>
#include <cuda_bf16.h>
#include <cuda.h>
#include <stdint.h>

namespace tbl {
constexpr double PI = 3.14159265358979323846264338327950288;
constexpr double sin_s(double x) { double t = x, s = x; for (int n = 1; n < 12; n++) { t *= -x * x / ((2 * n) * (2 * n + 1)); s += t; } return s; }
constexpr double cos_s(double x) { double t = 1, s = 1; for (int n = 1; n < 12; n++) { t *= -x * x / ((2 * n - 1) * (2 * n)); s += t; } return s; }
constexpr double cos2048(int m) {
  m &= 2047; if (m > 1024) m = 2048 - m;
  bool neg = false; if (m > 512) { m = 1024 - m; neg = true; }
  double v = (m <= 256) ? cos_s(2 * PI * m / 2048) : sin_s(2 * PI * (512 - m) / 2048);
  return neg ? -v : v;
}
constexpr uint16_t to_bf16(double v) {
  if (v == 0) return 0;
  uint16_t s = 0; if (v < 0) { s = 0x8000; v = -v; }
  int e = 0; while (v >= 2) { v /= 2; e++; } while (v < 1) { v *= 2; e--; }
  double m = (v - 1) * 128; int mi = (int)m; double fr = m - mi;
  if (fr > 0.5 || (fr == 0.5 && (mi & 1))) mi++;
  if (mi == 128) { mi = 0; e++; }
  return (uint16_t)(s | ((e + 127) << 7) | mi);
}
struct CosT { uint16_t v[2048]; constexpr CosT() : v() { for (int i = 0; i < 2048; i++) v[i] = to_bf16(cos2048(i)); } };
struct alignas(1024) FT {
  uint16_t v[512 * 512];
  constexpr FT() : v() {
    CosT c;
    for (int r = 0; r < 512; r++) {
      int k = (r >> 4) * 8 + (r & 7), e = (r >> 3) & 1;
      int mul = 4 * k, add = e ? 512 : 0;
      if (k == 0 && e == 1) { mul = 1024; add = 0; }
      for (int d = 0; d < 512; d++) v[r * 512 + d] = c.v[(d * mul + add) & 2047];
    }
  }
};
struct alignas(1024) ET {
  uint16_t v[2048 * 128];
  constexpr ET() : v() {
    CosT c;
    for (int s = 0; s < 2048; s++)
      for (int j = 0; j < 64; j++) {
        const int o = (s & 31) * 8192 + (s >> 5) * 64 + j;
        v[o] = c.v[(s * j) & 2047]; v[o + 4096] = c.v[(s * j + 512) & 2047];
      }
  }
};
struct alignas(1024) DT {
  uint16_t v[64 * 64];
  constexpr DT() : v() {
    CosT c;
    for (int r = 0; r < 64; r++)
      for (int n = 0; n < 64; n++) {
        const int sg = r >> 1, s0 = (sg & ~6) | ((sg & 2) << 1) | ((sg & 4) >> 1), e = r & 1, f = n & 1;
        const int m = 64 * s0 * (n >> 1) + (e == f ? 0 : e ? -512 : 512);
        v[r * 64 + (((n >> 3) ^ (r & 7)) << 3) + (n & 7)] = c.v[m & 2047];
      }
  }
};
}

__device__ constexpr tbl::FT g_FT = tbl::FT();
__device__ constexpr tbl::ET g_ET = tbl::ET();
__device__ constexpr tbl::DT g_DT = tbl::DT();

struct alignas(1024) Work {
  unsigned epoch[132 * 8];
  unsigned cntX[8 * 32], cntT[8 * 32], cntP[128 * 32], cntW[32], cntH[32];
  alignas(16) float gate[16 * 128];
  alignas(16) uint2 Wh[2 * 2048];
  alignas(16) uint2 Ts[32 * 64];
  alignas(1024) uint16_t X[129 * 8192];
  alignas(1024) uint16_t T[32 * 64 * 512];
  alignas(1024) uint4 part[128 * 3 * 1024];
};
__device__ Work g_work;
#define PROF_EV(i) do {} while (0)
#define PROF_CK(i) do {} while (0)

__device__ __forceinline__ uint32_t smem_u32(const void* p) { return (uint32_t)__cvta_generic_to_shared(p); }
__device__ __forceinline__ void mbar_init(uint32_t bar, uint32_t cnt) { asm volatile("mbarrier.init.shared::cta.b64 [%0], %1;" ::"r"(bar), "r"(cnt)); }
__device__ __forceinline__ void mbar_expect_tx(uint32_t bar, uint32_t bytes) { asm volatile("mbarrier.arrive.expect_tx.shared::cta.b64 _, [%0], %1;" ::"r"(bar), "r"(bytes) : "memory"); }
__device__ __forceinline__ void mbar_arrive(uint32_t bar) { asm volatile("mbarrier.arrive.shared::cta.b64 _, [%0];" ::"r"(bar) : "memory"); }
__device__ __forceinline__ bool elect_one() {
  uint32_t p;
  asm volatile("{\n.reg .pred p;\nelect.sync _|p, 0xffffffff;\nselp.u32 %0, 1, 0, p;\n}" : "=r"(p));
  return p;
}
__device__ __forceinline__ void mbar_arrive_if(bool p, uint32_t bar) {
  asm volatile("{\n.reg .pred p;\nsetp.ne.b32 p, %1, 0;\n@p mbarrier.arrive.shared::cta.b64 _, [%0];\n}" ::"r"(bar), "r"((int)p) : "memory");
}
__device__ __forceinline__ void hint_add_if(bool p, unsigned* a) {
  asm volatile("{\n.reg .pred p;\nsetp.ne.b32 p, %1, 0;\n@p red.relaxed.gpu.global.add.u32 [%0], 1;\n}" ::"l"(a), "r"((int)p) : "memory");
}
__device__ __forceinline__ bool mbar_try(uint32_t bar, uint32_t parity) {
  uint32_t ok;
  asm volatile("{\n.reg .pred p;\nmbarrier.test_wait.parity.shared::cta.b64 p, [%1], %2;\nselp.u32 %0, 1, 0, p;\n}" : "=r"(ok) : "r"(bar), "r"(parity) : "memory");
  return ok;
}
__device__ __forceinline__ void mbar_wait(uint32_t bar, uint32_t parity) {
  asm volatile(
      "{\n.reg .pred p;\n.reg .u32 n;\nmov.u32 n, 0;\n"
      "W_LOOP:\nmbarrier.try_wait.parity.shared::cta.b64 p, [%0], %1;\n@p bra W_DONE;\n"
      "add.u32 n, n, 1;\nsetp.lt.u32 p, n, 0x40000;\n@p bra W_LOOP;\ntrap;\nW_DONE:\n}" ::"r"(bar), "r"(parity) : "memory");
}
__device__ __forceinline__ void bulk_load(uint32_t dst, const void* src, uint32_t bytes, uint32_t bar) {
  asm volatile("cp.async.bulk.shared::cluster.global.mbarrier::complete_tx::bytes [%0], [%1], %2, [%3];" ::"r"(dst), "l"(src), "r"(bytes), "r"(bar) : "memory");
}
__device__ __forceinline__ void spin_guard(uint32_t t0) { if ((uint32_t)clock() - t0 > (1u << 30)) __trap(); }
__device__ __forceinline__ float2 ld_x2(const float2* p) { float2 v; asm volatile("ld.relaxed.gpu.global.v2.f32 {%0,%1}, [%2];" : "=f"(v.x), "=f"(v.y) : "l"(p) : "memory"); return v; }
__device__ __forceinline__ void st_u2(uint2* p, uint32_t a, uint32_t b) { asm volatile("st.relaxed.gpu.global.v2.u32 [%0], {%1,%2};" ::"l"(p), "r"(a), "r"(b) : "memory"); }
__device__ __forceinline__ uint32_t ld_x1(const void* p) { uint32_t v; asm volatile("ld.relaxed.gpu.global.u32 %0, [%1];" : "=r"(v) : "l"(p) : "memory"); return v; }
__device__ __forceinline__ uint4 ld_x4(const void* p) { uint4 v; asm volatile("ld.relaxed.gpu.global.v4.u32 {%0,%1,%2,%3}, [%4];" : "=r"(v.x), "=r"(v.y), "=r"(v.z), "=r"(v.w) : "l"(p) : "memory"); return v; }
__device__ __forceinline__ uint32_t mapa(uint32_t a, uint32_t cta) { uint32_t r; asm volatile("mapa.shared::cluster.u32 %0, %1, %2;" : "=r"(r) : "r"(a), "r"(cta)); return r; }
__device__ __forceinline__ void stsm4t(uint32_t a, uint32_t r0, uint32_t r1, uint32_t r2, uint32_t r3) {
  asm volatile("stmatrix.sync.aligned.m8n8.x4.trans.shared.b16 [%0], {%1,%2,%3,%4};" ::"r"(a), "r"(r0), "r"(r1), "r"(r2), "r"(r3) : "memory");
}
__device__ __forceinline__ void hint_add(unsigned* p) { asm volatile("red.relaxed.gpu.global.add.u32 [%0], 1;" ::"l"(p) : "memory"); }
__device__ __forceinline__ void hint_wait(const unsigned* p, unsigned target) {
  const uint32_t t0 = (uint32_t)clock();
  while ((int)(ld_x1(p) - target) < 0) spin_guard(t0);
}
__device__ __forceinline__ void bulk_done_signal(unsigned* p) {
  asm volatile("cp.async.bulk.commit_group;\ncp.async.bulk.wait_group 0;\nfence.proxy.async.global;" ::: "memory");
  hint_add(p);
}
__device__ __forceinline__ void flag_wait(const unsigned* p, unsigned target) {
  hint_wait(p, target);
  asm volatile("fence.proxy.async.global;" ::: "memory");
}
__device__ __forceinline__ void tma2d(uint32_t dst, const CUtensorMap* m, uint32_t bar, int c0, int c1) {
  asm volatile("cp.async.bulk.tensor.2d.shared::cluster.global.mbarrier::complete_tx::bytes [%0], [%1, {%3, %4}], [%2];" ::"r"(dst), "l"(m), "r"(bar), "r"(c0), "r"(c1) : "memory");
}
__device__ __forceinline__ void tma3d(uint32_t dst, const CUtensorMap* m, uint32_t bar, int c0, int c1, int c2) {
  asm volatile("cp.async.bulk.tensor.3d.shared::cluster.global.mbarrier::complete_tx::bytes [%0], [%1, {%3, %4, %5}], [%2];" ::"r"(dst), "l"(m), "r"(bar), "r"(c0), "r"(c1), "r"(c2) : "memory");
}
__device__ __forceinline__ void tma4d(uint32_t dst, const CUtensorMap* m, uint32_t bar, int c0, int c1, int c2, int c3) {
  asm volatile("cp.async.bulk.tensor.4d.shared::cluster.global.mbarrier::complete_tx::bytes [%0], [%1, {%3, %4, %5, %6}], [%2];" ::"r"(dst), "l"(m), "r"(bar), "r"(c0), "r"(c1), "r"(c2), "r"(c3) : "memory");
}
__device__ __forceinline__ void wg_fence() { asm volatile("wgmma.fence.sync.aligned;" ::: "memory"); }
__device__ __forceinline__ void wg_commit() { asm volatile("wgmma.commit_group.sync.aligned;" ::: "memory"); }
template <int N> __device__ __forceinline__ void wg_wait() { asm volatile("wgmma.wait_group.sync.aligned %0;" ::"n"(N) : "memory"); }
template <int O, int N, int NN> __device__ __forceinline__ void fence_regs(float (&d)[NN]) {
#pragma unroll
  for (int i = 0; i < N; i++) asm volatile("" : "+f"(d[O + i])::"memory");
}
__device__ __forceinline__ uint32_t pack_bf16(float lo, float hi) {
  uint32_t r; asm("cvt.rn.bf16x2.f32 %0, %1, %2;" : "=r"(r) : "f"(hi), "f"(lo)); return r;
}
__device__ __forceinline__ uint32_t pack_pin(float lo, float hi) {
  uint32_t r; asm volatile("cvt.rn.bf16x2.f32 %0, %1, %2;" : "=r"(r) : "f"(hi), "f"(lo) : "memory"); return r;
}
__device__ __forceinline__ uint32_t add_bf2(uint32_t a, uint32_t b) { uint32_t r; asm("add.rn.bf16x2 %0, %1, %2;" : "=r"(r) : "r"(a), "r"(b)); return r; }
__device__ __forceinline__ float bf_lo(uint32_t u) { return __uint_as_float(u << 16); }
__device__ __forceinline__ float bf_hi(uint32_t u) { return __uint_as_float(u & 0xffff0000u); }

__device__ __forceinline__ uint64_t d128(uint32_t lo) { uint64_t d; asm("mov.b64 %0, {%1, 0x40000040};" : "=l"(d) : "r"(lo)); return d; }
__device__ __forceinline__ uint64_t d64(uint32_t lo) { uint64_t d; asm("mov.b64 %0, {%1, 0x80000020};" : "=l"(d) : "r"(lo)); return d; }
template<int O,int TB,int ACC,int NN> __device__ __forceinline__ void mma_ss64(float (&d)[NN], uint64_t da, uint64_t db, int sd = 0){
  if constexpr (ACC == 1) asm volatile("wgmma.mma_async.sync.aligned.m64n64k16.f32.bf16.bf16 {%0,%1,%2,%3,%4,%5,%6,%7,%8,%9,%10,%11,%12,%13,%14,%15,%16,%17,%18,%19,%20,%21,%22,%23,%24,%25,%26,%27,%28,%29,%30,%31}, %32, %33, 1, 1, 1, %35, %34;"
   : "+f"(d[O+0]), "+f"(d[O+1]), "+f"(d[O+2]), "+f"(d[O+3]), "+f"(d[O+4]), "+f"(d[O+5]), "+f"(d[O+6]), "+f"(d[O+7]), "+f"(d[O+8]), "+f"(d[O+9]), "+f"(d[O+10]), "+f"(d[O+11]), "+f"(d[O+12]), "+f"(d[O+13]), "+f"(d[O+14]), "+f"(d[O+15]), "+f"(d[O+16]), "+f"(d[O+17]), "+f"(d[O+18]), "+f"(d[O+19]), "+f"(d[O+20]), "+f"(d[O+21]), "+f"(d[O+22]), "+f"(d[O+23]), "+f"(d[O+24]), "+f"(d[O+25]), "+f"(d[O+26]), "+f"(d[O+27]), "+f"(d[O+28]), "+f"(d[O+29]), "+f"(d[O+30]), "+f"(d[O+31])
   : "l"(da), "l"(db), "n"(TB & 1), "n"(TB >> 1));
  else if constexpr (ACC == 0) asm volatile("wgmma.mma_async.sync.aligned.m64n64k16.f32.bf16.bf16 {%0,%1,%2,%3,%4,%5,%6,%7,%8,%9,%10,%11,%12,%13,%14,%15,%16,%17,%18,%19,%20,%21,%22,%23,%24,%25,%26,%27,%28,%29,%30,%31}, %32, %33, 0, 1, 1, %35, %34;"
   : "=f"(d[O+0]), "=f"(d[O+1]), "=f"(d[O+2]), "=f"(d[O+3]), "=f"(d[O+4]), "=f"(d[O+5]), "=f"(d[O+6]), "=f"(d[O+7]), "=f"(d[O+8]), "=f"(d[O+9]), "=f"(d[O+10]), "=f"(d[O+11]), "=f"(d[O+12]), "=f"(d[O+13]), "=f"(d[O+14]), "=f"(d[O+15]), "=f"(d[O+16]), "=f"(d[O+17]), "=f"(d[O+18]), "=f"(d[O+19]), "=f"(d[O+20]), "=f"(d[O+21]), "=f"(d[O+22]), "=f"(d[O+23]), "=f"(d[O+24]), "=f"(d[O+25]), "=f"(d[O+26]), "=f"(d[O+27]), "=f"(d[O+28]), "=f"(d[O+29]), "=f"(d[O+30]), "=f"(d[O+31])
   : "l"(da), "l"(db), "n"(TB & 1), "n"(TB >> 1));
  else asm volatile("{\n.reg .pred p;\nsetp.ne.b32 p, %36, 0;\nwgmma.mma_async.sync.aligned.m64n64k16.f32.bf16.bf16 {%0,%1,%2,%3,%4,%5,%6,%7,%8,%9,%10,%11,%12,%13,%14,%15,%16,%17,%18,%19,%20,%21,%22,%23,%24,%25,%26,%27,%28,%29,%30,%31}, %32, %33, p, 1, 1, %35, %34;\n}"
   : "+f"(d[O+0]), "+f"(d[O+1]), "+f"(d[O+2]), "+f"(d[O+3]), "+f"(d[O+4]), "+f"(d[O+5]), "+f"(d[O+6]), "+f"(d[O+7]), "+f"(d[O+8]), "+f"(d[O+9]), "+f"(d[O+10]), "+f"(d[O+11]), "+f"(d[O+12]), "+f"(d[O+13]), "+f"(d[O+14]), "+f"(d[O+15]), "+f"(d[O+16]), "+f"(d[O+17]), "+f"(d[O+18]), "+f"(d[O+19]), "+f"(d[O+20]), "+f"(d[O+21]), "+f"(d[O+22]), "+f"(d[O+23]), "+f"(d[O+24]), "+f"(d[O+25]), "+f"(d[O+26]), "+f"(d[O+27]), "+f"(d[O+28]), "+f"(d[O+29]), "+f"(d[O+30]), "+f"(d[O+31])
   : "l"(da), "l"(db), "n"(TB & 1), "n"(TB >> 1), "r"(sd));
}
template<int O,int TB,int ACC,int NN> __device__ __forceinline__ void mma_rs64(float (&d)[NN], uint32_t a0, uint32_t a1, uint32_t a2, uint32_t a3, uint64_t db, int sd = 0){
  if constexpr (ACC == 1) asm volatile("wgmma.mma_async.sync.aligned.m64n64k16.f32.bf16.bf16 {%0,%1,%2,%3,%4,%5,%6,%7,%8,%9,%10,%11,%12,%13,%14,%15,%16,%17,%18,%19,%20,%21,%22,%23,%24,%25,%26,%27,%28,%29,%30,%31}, {%32,%33,%34,%35}, %36, 1, 1, 1, %37;"
   : "+f"(d[O+0]), "+f"(d[O+1]), "+f"(d[O+2]), "+f"(d[O+3]), "+f"(d[O+4]), "+f"(d[O+5]), "+f"(d[O+6]), "+f"(d[O+7]), "+f"(d[O+8]), "+f"(d[O+9]), "+f"(d[O+10]), "+f"(d[O+11]), "+f"(d[O+12]), "+f"(d[O+13]), "+f"(d[O+14]), "+f"(d[O+15]), "+f"(d[O+16]), "+f"(d[O+17]), "+f"(d[O+18]), "+f"(d[O+19]), "+f"(d[O+20]), "+f"(d[O+21]), "+f"(d[O+22]), "+f"(d[O+23]), "+f"(d[O+24]), "+f"(d[O+25]), "+f"(d[O+26]), "+f"(d[O+27]), "+f"(d[O+28]), "+f"(d[O+29]), "+f"(d[O+30]), "+f"(d[O+31])
   : "r"(a0), "r"(a1), "r"(a2), "r"(a3), "l"(db), "n"(TB));
  else if constexpr (ACC == 0) asm volatile("wgmma.mma_async.sync.aligned.m64n64k16.f32.bf16.bf16 {%0,%1,%2,%3,%4,%5,%6,%7,%8,%9,%10,%11,%12,%13,%14,%15,%16,%17,%18,%19,%20,%21,%22,%23,%24,%25,%26,%27,%28,%29,%30,%31}, {%32,%33,%34,%35}, %36, 0, 1, 1, %37;"
   : "=f"(d[O+0]), "=f"(d[O+1]), "=f"(d[O+2]), "=f"(d[O+3]), "=f"(d[O+4]), "=f"(d[O+5]), "=f"(d[O+6]), "=f"(d[O+7]), "=f"(d[O+8]), "=f"(d[O+9]), "=f"(d[O+10]), "=f"(d[O+11]), "=f"(d[O+12]), "=f"(d[O+13]), "=f"(d[O+14]), "=f"(d[O+15]), "=f"(d[O+16]), "=f"(d[O+17]), "=f"(d[O+18]), "=f"(d[O+19]), "=f"(d[O+20]), "=f"(d[O+21]), "=f"(d[O+22]), "=f"(d[O+23]), "=f"(d[O+24]), "=f"(d[O+25]), "=f"(d[O+26]), "=f"(d[O+27]), "=f"(d[O+28]), "=f"(d[O+29]), "=f"(d[O+30]), "=f"(d[O+31])
   : "r"(a0), "r"(a1), "r"(a2), "r"(a3), "l"(db), "n"(TB));
  else asm volatile("{\n.reg .pred p;\nsetp.ne.b32 p, %38, 0;\nwgmma.mma_async.sync.aligned.m64n64k16.f32.bf16.bf16 {%0,%1,%2,%3,%4,%5,%6,%7,%8,%9,%10,%11,%12,%13,%14,%15,%16,%17,%18,%19,%20,%21,%22,%23,%24,%25,%26,%27,%28,%29,%30,%31}, {%32,%33,%34,%35}, %36, p, 1, 1, %37;\n}"
   : "+f"(d[O+0]), "+f"(d[O+1]), "+f"(d[O+2]), "+f"(d[O+3]), "+f"(d[O+4]), "+f"(d[O+5]), "+f"(d[O+6]), "+f"(d[O+7]), "+f"(d[O+8]), "+f"(d[O+9]), "+f"(d[O+10]), "+f"(d[O+11]), "+f"(d[O+12]), "+f"(d[O+13]), "+f"(d[O+14]), "+f"(d[O+15]), "+f"(d[O+16]), "+f"(d[O+17]), "+f"(d[O+18]), "+f"(d[O+19]), "+f"(d[O+20]), "+f"(d[O+21]), "+f"(d[O+22]), "+f"(d[O+23]), "+f"(d[O+24]), "+f"(d[O+25]), "+f"(d[O+26]), "+f"(d[O+27]), "+f"(d[O+28]), "+f"(d[O+29]), "+f"(d[O+30]), "+f"(d[O+31])
   : "r"(a0), "r"(a1), "r"(a2), "r"(a3), "l"(db), "n"(TB), "r"(sd));
}
template<int O,int TB,int ACC,int NN> __device__ __forceinline__ void mma_ss128(float (&d)[NN], uint64_t da, uint64_t db, int sd = 0){
  if constexpr (ACC == 1) asm volatile("wgmma.mma_async.sync.aligned.m64n128k16.f32.bf16.bf16 {%0,%1,%2,%3,%4,%5,%6,%7,%8,%9,%10,%11,%12,%13,%14,%15,%16,%17,%18,%19,%20,%21,%22,%23,%24,%25,%26,%27,%28,%29,%30,%31,%32,%33,%34,%35,%36,%37,%38,%39,%40,%41,%42,%43,%44,%45,%46,%47,%48,%49,%50,%51,%52,%53,%54,%55,%56,%57,%58,%59,%60,%61,%62,%63}, %64, %65, 1, 1, 1, %67, %66;"
   : "+f"(d[O+0]), "+f"(d[O+1]), "+f"(d[O+2]), "+f"(d[O+3]), "+f"(d[O+4]), "+f"(d[O+5]), "+f"(d[O+6]), "+f"(d[O+7]), "+f"(d[O+8]), "+f"(d[O+9]), "+f"(d[O+10]), "+f"(d[O+11]), "+f"(d[O+12]), "+f"(d[O+13]), "+f"(d[O+14]), "+f"(d[O+15]), "+f"(d[O+16]), "+f"(d[O+17]), "+f"(d[O+18]), "+f"(d[O+19]), "+f"(d[O+20]), "+f"(d[O+21]), "+f"(d[O+22]), "+f"(d[O+23]), "+f"(d[O+24]), "+f"(d[O+25]), "+f"(d[O+26]), "+f"(d[O+27]), "+f"(d[O+28]), "+f"(d[O+29]), "+f"(d[O+30]), "+f"(d[O+31]), "+f"(d[O+32]), "+f"(d[O+33]), "+f"(d[O+34]), "+f"(d[O+35]), "+f"(d[O+36]), "+f"(d[O+37]), "+f"(d[O+38]), "+f"(d[O+39]), "+f"(d[O+40]), "+f"(d[O+41]), "+f"(d[O+42]), "+f"(d[O+43]), "+f"(d[O+44]), "+f"(d[O+45]), "+f"(d[O+46]), "+f"(d[O+47]), "+f"(d[O+48]), "+f"(d[O+49]), "+f"(d[O+50]), "+f"(d[O+51]), "+f"(d[O+52]), "+f"(d[O+53]), "+f"(d[O+54]), "+f"(d[O+55]), "+f"(d[O+56]), "+f"(d[O+57]), "+f"(d[O+58]), "+f"(d[O+59]), "+f"(d[O+60]), "+f"(d[O+61]), "+f"(d[O+62]), "+f"(d[O+63])
   : "l"(da), "l"(db), "n"(TB & 1), "n"(TB >> 1));
  else if constexpr (ACC == 0) asm volatile("wgmma.mma_async.sync.aligned.m64n128k16.f32.bf16.bf16 {%0,%1,%2,%3,%4,%5,%6,%7,%8,%9,%10,%11,%12,%13,%14,%15,%16,%17,%18,%19,%20,%21,%22,%23,%24,%25,%26,%27,%28,%29,%30,%31,%32,%33,%34,%35,%36,%37,%38,%39,%40,%41,%42,%43,%44,%45,%46,%47,%48,%49,%50,%51,%52,%53,%54,%55,%56,%57,%58,%59,%60,%61,%62,%63}, %64, %65, 0, 1, 1, %67, %66;"
   : "=f"(d[O+0]), "=f"(d[O+1]), "=f"(d[O+2]), "=f"(d[O+3]), "=f"(d[O+4]), "=f"(d[O+5]), "=f"(d[O+6]), "=f"(d[O+7]), "=f"(d[O+8]), "=f"(d[O+9]), "=f"(d[O+10]), "=f"(d[O+11]), "=f"(d[O+12]), "=f"(d[O+13]), "=f"(d[O+14]), "=f"(d[O+15]), "=f"(d[O+16]), "=f"(d[O+17]), "=f"(d[O+18]), "=f"(d[O+19]), "=f"(d[O+20]), "=f"(d[O+21]), "=f"(d[O+22]), "=f"(d[O+23]), "=f"(d[O+24]), "=f"(d[O+25]), "=f"(d[O+26]), "=f"(d[O+27]), "=f"(d[O+28]), "=f"(d[O+29]), "=f"(d[O+30]), "=f"(d[O+31]), "=f"(d[O+32]), "=f"(d[O+33]), "=f"(d[O+34]), "=f"(d[O+35]), "=f"(d[O+36]), "=f"(d[O+37]), "=f"(d[O+38]), "=f"(d[O+39]), "=f"(d[O+40]), "=f"(d[O+41]), "=f"(d[O+42]), "=f"(d[O+43]), "=f"(d[O+44]), "=f"(d[O+45]), "=f"(d[O+46]), "=f"(d[O+47]), "=f"(d[O+48]), "=f"(d[O+49]), "=f"(d[O+50]), "=f"(d[O+51]), "=f"(d[O+52]), "=f"(d[O+53]), "=f"(d[O+54]), "=f"(d[O+55]), "=f"(d[O+56]), "=f"(d[O+57]), "=f"(d[O+58]), "=f"(d[O+59]), "=f"(d[O+60]), "=f"(d[O+61]), "=f"(d[O+62]), "=f"(d[O+63])
   : "l"(da), "l"(db), "n"(TB & 1), "n"(TB >> 1));
  else asm volatile("{\n.reg .pred p;\nsetp.ne.b32 p, %68, 0;\nwgmma.mma_async.sync.aligned.m64n128k16.f32.bf16.bf16 {%0,%1,%2,%3,%4,%5,%6,%7,%8,%9,%10,%11,%12,%13,%14,%15,%16,%17,%18,%19,%20,%21,%22,%23,%24,%25,%26,%27,%28,%29,%30,%31,%32,%33,%34,%35,%36,%37,%38,%39,%40,%41,%42,%43,%44,%45,%46,%47,%48,%49,%50,%51,%52,%53,%54,%55,%56,%57,%58,%59,%60,%61,%62,%63}, %64, %65, p, 1, 1, %67, %66;\n}"
   : "+f"(d[O+0]), "+f"(d[O+1]), "+f"(d[O+2]), "+f"(d[O+3]), "+f"(d[O+4]), "+f"(d[O+5]), "+f"(d[O+6]), "+f"(d[O+7]), "+f"(d[O+8]), "+f"(d[O+9]), "+f"(d[O+10]), "+f"(d[O+11]), "+f"(d[O+12]), "+f"(d[O+13]), "+f"(d[O+14]), "+f"(d[O+15]), "+f"(d[O+16]), "+f"(d[O+17]), "+f"(d[O+18]), "+f"(d[O+19]), "+f"(d[O+20]), "+f"(d[O+21]), "+f"(d[O+22]), "+f"(d[O+23]), "+f"(d[O+24]), "+f"(d[O+25]), "+f"(d[O+26]), "+f"(d[O+27]), "+f"(d[O+28]), "+f"(d[O+29]), "+f"(d[O+30]), "+f"(d[O+31]), "+f"(d[O+32]), "+f"(d[O+33]), "+f"(d[O+34]), "+f"(d[O+35]), "+f"(d[O+36]), "+f"(d[O+37]), "+f"(d[O+38]), "+f"(d[O+39]), "+f"(d[O+40]), "+f"(d[O+41]), "+f"(d[O+42]), "+f"(d[O+43]), "+f"(d[O+44]), "+f"(d[O+45]), "+f"(d[O+46]), "+f"(d[O+47]), "+f"(d[O+48]), "+f"(d[O+49]), "+f"(d[O+50]), "+f"(d[O+51]), "+f"(d[O+52]), "+f"(d[O+53]), "+f"(d[O+54]), "+f"(d[O+55]), "+f"(d[O+56]), "+f"(d[O+57]), "+f"(d[O+58]), "+f"(d[O+59]), "+f"(d[O+60]), "+f"(d[O+61]), "+f"(d[O+62]), "+f"(d[O+63])
   : "l"(da), "l"(db), "n"(TB & 1), "n"(TB >> 1), "r"(sd));
}
template<int O,int TB,int ACC,int NN> __device__ __forceinline__ void mma_rs128(float (&d)[NN], uint32_t a0, uint32_t a1, uint32_t a2, uint32_t a3, uint64_t db, int sd = 0){
  if constexpr (ACC == 1) asm volatile("wgmma.mma_async.sync.aligned.m64n128k16.f32.bf16.bf16 {%0,%1,%2,%3,%4,%5,%6,%7,%8,%9,%10,%11,%12,%13,%14,%15,%16,%17,%18,%19,%20,%21,%22,%23,%24,%25,%26,%27,%28,%29,%30,%31,%32,%33,%34,%35,%36,%37,%38,%39,%40,%41,%42,%43,%44,%45,%46,%47,%48,%49,%50,%51,%52,%53,%54,%55,%56,%57,%58,%59,%60,%61,%62,%63}, {%64,%65,%66,%67}, %68, 1, 1, 1, %69;"
   : "+f"(d[O+0]), "+f"(d[O+1]), "+f"(d[O+2]), "+f"(d[O+3]), "+f"(d[O+4]), "+f"(d[O+5]), "+f"(d[O+6]), "+f"(d[O+7]), "+f"(d[O+8]), "+f"(d[O+9]), "+f"(d[O+10]), "+f"(d[O+11]), "+f"(d[O+12]), "+f"(d[O+13]), "+f"(d[O+14]), "+f"(d[O+15]), "+f"(d[O+16]), "+f"(d[O+17]), "+f"(d[O+18]), "+f"(d[O+19]), "+f"(d[O+20]), "+f"(d[O+21]), "+f"(d[O+22]), "+f"(d[O+23]), "+f"(d[O+24]), "+f"(d[O+25]), "+f"(d[O+26]), "+f"(d[O+27]), "+f"(d[O+28]), "+f"(d[O+29]), "+f"(d[O+30]), "+f"(d[O+31]), "+f"(d[O+32]), "+f"(d[O+33]), "+f"(d[O+34]), "+f"(d[O+35]), "+f"(d[O+36]), "+f"(d[O+37]), "+f"(d[O+38]), "+f"(d[O+39]), "+f"(d[O+40]), "+f"(d[O+41]), "+f"(d[O+42]), "+f"(d[O+43]), "+f"(d[O+44]), "+f"(d[O+45]), "+f"(d[O+46]), "+f"(d[O+47]), "+f"(d[O+48]), "+f"(d[O+49]), "+f"(d[O+50]), "+f"(d[O+51]), "+f"(d[O+52]), "+f"(d[O+53]), "+f"(d[O+54]), "+f"(d[O+55]), "+f"(d[O+56]), "+f"(d[O+57]), "+f"(d[O+58]), "+f"(d[O+59]), "+f"(d[O+60]), "+f"(d[O+61]), "+f"(d[O+62]), "+f"(d[O+63])
   : "r"(a0), "r"(a1), "r"(a2), "r"(a3), "l"(db), "n"(TB));
  else if constexpr (ACC == 0) asm volatile("wgmma.mma_async.sync.aligned.m64n128k16.f32.bf16.bf16 {%0,%1,%2,%3,%4,%5,%6,%7,%8,%9,%10,%11,%12,%13,%14,%15,%16,%17,%18,%19,%20,%21,%22,%23,%24,%25,%26,%27,%28,%29,%30,%31,%32,%33,%34,%35,%36,%37,%38,%39,%40,%41,%42,%43,%44,%45,%46,%47,%48,%49,%50,%51,%52,%53,%54,%55,%56,%57,%58,%59,%60,%61,%62,%63}, {%64,%65,%66,%67}, %68, 0, 1, 1, %69;"
   : "=f"(d[O+0]), "=f"(d[O+1]), "=f"(d[O+2]), "=f"(d[O+3]), "=f"(d[O+4]), "=f"(d[O+5]), "=f"(d[O+6]), "=f"(d[O+7]), "=f"(d[O+8]), "=f"(d[O+9]), "=f"(d[O+10]), "=f"(d[O+11]), "=f"(d[O+12]), "=f"(d[O+13]), "=f"(d[O+14]), "=f"(d[O+15]), "=f"(d[O+16]), "=f"(d[O+17]), "=f"(d[O+18]), "=f"(d[O+19]), "=f"(d[O+20]), "=f"(d[O+21]), "=f"(d[O+22]), "=f"(d[O+23]), "=f"(d[O+24]), "=f"(d[O+25]), "=f"(d[O+26]), "=f"(d[O+27]), "=f"(d[O+28]), "=f"(d[O+29]), "=f"(d[O+30]), "=f"(d[O+31]), "=f"(d[O+32]), "=f"(d[O+33]), "=f"(d[O+34]), "=f"(d[O+35]), "=f"(d[O+36]), "=f"(d[O+37]), "=f"(d[O+38]), "=f"(d[O+39]), "=f"(d[O+40]), "=f"(d[O+41]), "=f"(d[O+42]), "=f"(d[O+43]), "=f"(d[O+44]), "=f"(d[O+45]), "=f"(d[O+46]), "=f"(d[O+47]), "=f"(d[O+48]), "=f"(d[O+49]), "=f"(d[O+50]), "=f"(d[O+51]), "=f"(d[O+52]), "=f"(d[O+53]), "=f"(d[O+54]), "=f"(d[O+55]), "=f"(d[O+56]), "=f"(d[O+57]), "=f"(d[O+58]), "=f"(d[O+59]), "=f"(d[O+60]), "=f"(d[O+61]), "=f"(d[O+62]), "=f"(d[O+63])
   : "r"(a0), "r"(a1), "r"(a2), "r"(a3), "l"(db), "n"(TB));
  else asm volatile("{\n.reg .pred p;\nsetp.ne.b32 p, %70, 0;\nwgmma.mma_async.sync.aligned.m64n128k16.f32.bf16.bf16 {%0,%1,%2,%3,%4,%5,%6,%7,%8,%9,%10,%11,%12,%13,%14,%15,%16,%17,%18,%19,%20,%21,%22,%23,%24,%25,%26,%27,%28,%29,%30,%31,%32,%33,%34,%35,%36,%37,%38,%39,%40,%41,%42,%43,%44,%45,%46,%47,%48,%49,%50,%51,%52,%53,%54,%55,%56,%57,%58,%59,%60,%61,%62,%63}, {%64,%65,%66,%67}, %68, p, 1, 1, %69;\n}"
   : "+f"(d[O+0]), "+f"(d[O+1]), "+f"(d[O+2]), "+f"(d[O+3]), "+f"(d[O+4]), "+f"(d[O+5]), "+f"(d[O+6]), "+f"(d[O+7]), "+f"(d[O+8]), "+f"(d[O+9]), "+f"(d[O+10]), "+f"(d[O+11]), "+f"(d[O+12]), "+f"(d[O+13]), "+f"(d[O+14]), "+f"(d[O+15]), "+f"(d[O+16]), "+f"(d[O+17]), "+f"(d[O+18]), "+f"(d[O+19]), "+f"(d[O+20]), "+f"(d[O+21]), "+f"(d[O+22]), "+f"(d[O+23]), "+f"(d[O+24]), "+f"(d[O+25]), "+f"(d[O+26]), "+f"(d[O+27]), "+f"(d[O+28]), "+f"(d[O+29]), "+f"(d[O+30]), "+f"(d[O+31]), "+f"(d[O+32]), "+f"(d[O+33]), "+f"(d[O+34]), "+f"(d[O+35]), "+f"(d[O+36]), "+f"(d[O+37]), "+f"(d[O+38]), "+f"(d[O+39]), "+f"(d[O+40]), "+f"(d[O+41]), "+f"(d[O+42]), "+f"(d[O+43]), "+f"(d[O+44]), "+f"(d[O+45]), "+f"(d[O+46]), "+f"(d[O+47]), "+f"(d[O+48]), "+f"(d[O+49]), "+f"(d[O+50]), "+f"(d[O+51]), "+f"(d[O+52]), "+f"(d[O+53]), "+f"(d[O+54]), "+f"(d[O+55]), "+f"(d[O+56]), "+f"(d[O+57]), "+f"(d[O+58]), "+f"(d[O+59]), "+f"(d[O+60]), "+f"(d[O+61]), "+f"(d[O+62]), "+f"(d[O+63])
   : "r"(a0), "r"(a1), "r"(a2), "r"(a3), "l"(db), "n"(TB), "r"(sd));
}

#define NEARLY 0
#define XAHEAD 3
#define HEADN 6
#define WBATCH 1
#define WB 8
#define WSLEEP 20
#define XSPREAD 4
#define NOSEND 0
#define MSPLIT 3
#define PFALL 1
#define L2PF 0
#define STAG 0
#define EPF 2
#define XNB 2
#define FNB 0
#define GNB 0
#define TH 4
#define PF0 4
#define FSPLIT 1
#define MGLU 1
#define SPC 2
#define TL 14
#define GKB 4
#define T0A 7
#define SPACE 40
#define WPF 1
#define WAFTER 7
#define WPACE 0
#define GATE_AT 4
#define TPACE 40
#define PFMODE 0
#define MAPMODE 1
template <int V> struct IC { static constexpr int value = V; };
struct Maps { CUtensorMap x, ft, g64, u64, e, wr, wi, xs, ts, t, g32, u32, d224; };

constexpr int NCTA = 130;
constexpr int U = 16384;
constexpr int TB = 36864;
constexpr int OFF_RING = 8 * U, OFF_Z = 12 * U, OFF_XB = 12 * U, OFF_T = 13 * U, OFF_D = OFF_T;
constexpr int OFF_BAR = 14 * U, OFF_SP = OFF_BAR + 512, OFF_G = OFF_SP + 1024 + 128;
constexpr int SMEM_BYTES = OFF_G + 512;
constexpr int B_FX = 0, B_FA = 8, B_FT = 12, B_Z = 16, B_W = 24, B_HX = 25, B_TL = 26, B_HP = 27, B_WR = 30, B_E0 = 34;
constexpr int B_EA = 35, B_ET = 39, B_PZ = 43, B_RDY = 45, B_FE = 46;
constexpr int B_T = 50, B_XS = 51, B_G = 53, B_RD0 = 54, NBAR = 55;
__host__ __device__ constexpr int rslot(int n) { return n & 3; }
__host__ __device__ constexpr int rpar(int n) { return (n >> 2) & 1; }

__global__ void __cluster_dims__(2, 1, 1) __launch_bounds__(512, 1)
fused_kernel(Work* __restrict__ ws, const uint16_t* __restrict__ dtab, const __nv_bfloat16* __restrict__ w_r, const __nv_bfloat16* __restrict__ w_i,
             const __nv_bfloat16* __restrict__ gate_w, const __nv_bfloat16* __restrict__ x, __nv_bfloat16* __restrict__ out,
             const __grid_constant__ Maps maps) {
  extern __shared__ __align__(1024) uint8_t smem[];
  if (threadIdx.x < 32 && elect_one()) {
#pragma unroll
    for (int i = 0; i < PF0; i++) asm volatile("prefetch.tensormap [%0];" ::"l"((const char*)&maps + i * 128) : "memory");
  }
  const uint32_t sb = smem_u32(smem);
  const uint32_t bars = sb + OFF_BAR;
  const int tid = threadIdx.x, lane = tid & 31;
  const int warp = __shfl_sync(0xffffffffu, tid >> 5, 0);
  const bool helper = blockIdx.x >= 128;
  const int cl = (blockIdx.x >> 1) & 63, rank = blockIdx.x & 1;
  const int q4 = (cl & 1) | ((cl >> 2) & 2), rb = ((cl >> 1) & 3) | ((cl >> 4) << 2);
  const int j = 2 * q4 + rank;
  const int f_full = 448 * q4 + (rank ? 256 : 0);
  const int f_half = 448 * q4 + (rank ? 224 : 192);
  const int kg = 2 * j + (rb >> 3), tn = rb & 7;

  if (tid == 64) { PROF_EV(0); PROF_CK(40); }
  if (warp < 8) {
    if (!helper && tid < 32) {
      const int r = 16 * j + (tid & 15);
      asm volatile("prefetch.global.L2 [%0];" ::"l"(x + (size_t)(2 * rb + (r >> 6) + 32 * (r & 63)) * 512 + 64 * (tid >> 4)));
    }
    asm volatile("barrier.cluster.arrive.relaxed.aligned;" ::: "memory");
    asm volatile("setmaxnreg.inc.sync.aligned.u32 192;");
    if (!helper) {
      const int wg = warp >> 2, w = warp & 3, g = lane >> 2;
      const bool elect = (tid & 127) == 0;
      float cX[32], cA[64], cB[64], cC[64], ci[64], ct[64];
      const int zero = blockIdx.x >> 16;
      uint32_t h[56], yf[16];
      const uint32_t d0 = (sb & 0x3FFFF) >> 4;
      const uint32_t dK = d0 | (1u << 16), dN = d0 | (512u << 16);
      const uint32_t dX = dK + wg * 512;
      constexpr uint32_t RING = OFF_RING >> 4;
      auto waitA = [&](int n) { mbar_wait(bars + 8 * (B_FA + rslot(n)), rpar(n)); };
      auto freeA = [&](int n) { mbar_arrive_if(elect, bars + 8 * (B_EA + rslot(n))); };
      auto nop = [] {};

      asm volatile("bar.sync 0, 384;" ::: "memory");
#pragma unroll 1
      for (int i = 0; i < 4; i++) {
        const uint64_t dx = d128(dX + i * 2048), df = d128(dK + (OFF_XB >> 4) + (i & 1) * 1024);
        mbar_wait(bars + 8 * (B_FX + 2 * i), 0);
        wg_fence();
        mma_ss64<0, 0, 2>(cX, df, dx, i);
        mma_ss64<0, 0, 1>(cX, df + 2, dx + 2);
        wg_commit(); wg_wait<1>();
        mbar_arrive_if(elect && i, bars + 8 * (B_EA + rslot(i - 1)));
        mma_ss64<0, 0, 1>(cX, df + 4, dx + 4);
        mma_ss64<0, 0, 1>(cX, df + 6, dx + 6);
        if (i == 0 && tid == 0) PROF_EV(1);
        mbar_wait(bars + 8 * (B_FX + 2 * i + 1), 0);
        wg_fence();
#pragma unroll
        for (int k = 0; k < 4; k++) mma_ss64<0, 0, 1>(cX, df + (512 + k * 2), dx + (1024 + k * 2));
        wg_commit();
        waitA(i);
        wg_fence();
        const uint64_t da = d128(dX + i * 1024), db = d128(dN + RING + i * 1024);
        mma_ss128<0, 1, 2>(cA, da, db, i);
        wg_commit(); wg_wait<1>();
        mbar_arrive_if(elect, bars + 8 * (B_FE + i));
#pragma unroll
        for (int k = 1; k < 4; k++) mma_ss128<0, 1, 1>(cA, da + k * 2, db + k * 128);
        wg_commit();
      }
      fence_regs<0, 32>(cX);
#pragma unroll
      for (int e = 0; e < 16; e++) yf[e] = pack_pin(cX[2 * e], cX[2 * e + 1]);
      if (tid == 0) { PROF_EV(2); PROF_CK(42); }
      {
        waitA(4); mbar_wait(bars + 8 * B_E0, 0);
        const uint64_t de = d128(dN + (wg ? RING : OFF_XB >> 4));
        wg_fence();
        mma_rs128<0, 1, 0>(cB, yf[0], yf[1], yf[2], yf[3], de);
        wg_commit();
        wg_wait<1>();
        freeA(3);
#pragma unroll
        for (int k = 1; k < 4; k++) mma_rs128<0, 1, 1>(cB, yf[4 * k], yf[4 * k + 1], yf[4 * k + 2], yf[4 * k + 3], de + k * 128);
        wg_commit();
      }
      bool rel = false;
      auto acquire = [&](int n) {
        rel = elect;
        if (!mbar_try(bars + 8 * (B_FA + rslot(n)), rpar(n))) { wg_wait<0>(); freeA(n - 1); rel = false; waitA(n); }
      };
      auto freeP = [&](int n) { mbar_arrive_if(rel, bars + 8 * (B_EA + rslot(n - 1))); };
      auto ffn_step = [&](auto first, auto split, float (&acc)[64], int n, int kb, auto done, auto work) {
        constexpr int SPLIT = decltype(split)::value;
        acquire(n);
        wg_fence();
        const uint64_t dx = d128(dX + kb * 1024), db = d128(dN + RING + rslot(n) * 1024);
        mma_ss128<0, 1, decltype(first)::value>(acc, dx, db, kb);
#pragma unroll
        for (int k = 1; k < SPLIT; k++) mma_ss128<0, 1, 1>(acc, dx + k * 2, db + k * 128);
        wg_commit();
        work();
        wg_wait<1>();
        freeP(n);
        done();
        if (SPLIT < 4) {
          wg_fence();
#pragma unroll
          for (int k = SPLIT; k < 4; k++) mma_ss128<0, 1, 1>(acc, dx + k * 2, db + k * 128);
          wg_commit();
        }
      };
      {
        const int s0 = 2 * rb + wg, kr = 2 * ((s0 & 1) | ((s0 & 4) >> 1));
        const int m = lane >> 3, r = lane & 7;
        const uint32_t a0 = sb + OFF_XB + wg * 8192 + (((w >> 1) * 8 + (m >> 1)) * 2 + (w & 1)) * 256 + (m & 1) * 128 + ((r ^ (kr + (m & 1))) << 4);
        ffn_step(IC<1>(), IC<4>(), cA, 5, 4, [&] { fence_regs<0, 64>(cB); }, nop);
        asm volatile("bar.sync 5, 256;" ::: "memory");
        auto stage = [&](int i) {
          stsm4t(a0 + i * 1024, pack_bf16(cB[8 * i] - cB[34 + 8 * i], cB[8 * i + 1] - cB[35 + 8 * i]),
                 pack_bf16(cB[32 + 8 * i] + cB[8 * i + 2], cB[33 + 8 * i] + cB[8 * i + 3]),
                 pack_bf16(cB[8 * i + 4] - cB[38 + 8 * i], cB[8 * i + 5] - cB[39 + 8 * i]),
                 pack_bf16(cB[36 + 8 * i] + cB[8 * i + 6], cB[37 + 8 * i] + cB[8 * i + 7]));
          if (j == 0 && w == 0) {
            const uint32_t a1 = r ? sb + OFF_SP + 1024 : sb + OFF_SP + wg * 512 + (m & 1) * 256 + (m >> 1) * 128;
#pragma unroll
            for (int n = 2 * i; n < 2 * i + 2; n++)
              asm volatile("stmatrix.sync.aligned.m8n8.x4.shared.b16 [%0], {%1,%2,%3,%4};" ::"r"(a1 + ((n ^ (kr + (m >> 1)) ^ r) << 4)),
                           "r"(pack_bf16(cB[4 * n], cB[4 * n + 1])), "r"(pack_bf16(cB[4 * n + 2], cB[4 * n + 3])),
                           "r"(pack_bf16(cB[32 + 4 * n], cB[33 + 4 * n])), "r"(pack_bf16(cB[34 + 4 * n], cB[35 + 4 * n])) : "memory");
          }
        };
        auto publish = [&] {
          asm volatile("fence.proxy.async.shared::cta;" ::: "memory");
          __syncwarp();
          mbar_arrive_if(lane == 0, bars + 8 * (B_XS + wg));
          if (tid == 0) PROF_EV(3);
        };
        stage(0);
        ffn_step(IC<1>(), IC<FSPLIT>(), cA, 6, 5, nop, nop);
        stage(1);
        ffn_step(IC<1>(), IC<FSPLIT>(), cA, 7, 6, nop, nop);
        stage(2);
        ffn_step(IC<1>(), IC<2>(), cA, 8, 7, [&] { stage(3); }, nop);
        publish();
      }
      uint32_t gb0 = 0, gb1 = 0;
      uint32_t ob[2] = {0, 0};
      auto glu = [&](auto& acc, int half, int ho, int i0, int i1) {
#pragma unroll
        for (int i = i0; i < i1; i++)
          asm volatile("{\n.reg .b32 a, b;\ncvt.rn.relu.bf16x2.f32 a, %2, %1;\ncvt.rn.bf16x2.f32 b, %4, %3;\nmul.rn.bf16x2 a, a, b;\nmul.rn.bf16x2 %0, a, %5;\n}"
                       : "=r"(h[ho + i]) : "f"(acc[2 * i]), "f"(acc[2 * i + 1]), "f"(acc[half + 2 * i]), "f"(acc[half + 1 + 2 * i]), "r"(ob[i & 1]) : "memory");
      };
      ffn_step(IC<2>(), IC<1>(), cB, 9, zero, nop, nop);
#pragma unroll 1
      for (int kb = 1; kb < 8; kb++)
        ffn_step(IC<1>(), IC<FSPLIT>(), cB, 9 + kb, kb, nop, [&] {
          if (kb == GKB) {
            mbar_wait(bars + 8 * B_G, 0);
            asm volatile("ld.shared.u32 %0, [%2];\nld.shared.u32 %1, [%2+32];" : "=r"(gb0), "=r"(gb1) : "r"(sb + OFF_G + (wg * 64 + w * 16 + g) * 4) : "memory");
          } else if (kb == 5 + 2 * wg) {
            ob[0] = pack_bf16(1.0f - bf_hi(gb0), 1.0f - bf_hi(gb0)); ob[1] = pack_bf16(1.0f - bf_hi(gb1), 1.0f - bf_hi(gb1));
            glu(cA, 32, 0, 0, 16);
          }
        });
      const uint32_t tag = gb0 & 1;
      const float g0 = bf_hi(gb0), g1 = bf_hi(gb1);
      if (tid == 0) { PROF_EV(4); PROF_CK(43); }
      auto m_step = [&](auto first, int i) {
        acquire(17 + i);
        wg_fence();
        const uint64_t dx = d128(dX + i * 2048), dm = d64(dN + RING + rslot(17 + i) * 1024);
        mma_ss64<0, 1, decltype(first)::value>(ct, dx, dm);
#pragma unroll
        for (int k = 1; k < MSPLIT; k++) mma_ss64<0, 1, 1>(ct, dx + ((k >> 2) * 1024 + (k & 3) * 2), dm + k * 64);
        wg_commit();
        wg_wait<1>();
        freeP(17 + i);
        wg_fence();
#pragma unroll
        for (int k = MSPLIT; k < 8; k++) mma_ss64<0, 1, 1>(ct, dx + ((k >> 2) * 1024 + (k & 3) * 2), dm + k * 64);
        wg_commit();
      };
      m_step(IC<0>(), 0);
#pragma unroll 1
      for (int i = 1; i < 5; i++) {
        if (i == 1 + 2 * wg) glu(cB, 32, 16, 0, 16);
        if (i < 4) m_step(IC<1>(), i);
      }
      if (tid == 0) { PROF_EV(5); PROF_CK(44); }
      ffn_step(IC<0>(), IC<1>(), cC, 21, 0, nop, nop);
#pragma unroll 1
      for (int kb = 1; kb < 8; kb++)
        ffn_step(IC<1>(), IC<FSPLIT>(), cC, 21 + kb, kb, [&] { mbar_arrive_if(elect && !(kb & 1), bars + 8 * (B_ET + (kb >> 1) - 1)); }, [&] {
          if (kb == 1 + wg) glu(ct, 16, 48, 0, 8);
        });

      auto twait = [&](uint32_t bar, uint32_t par, int) { mbar_wait(bar, par); };
      const int fo = warp * 128 + lane;
      auto fetch = [&](uint4 (&pv)[4], int z) {
        twait(bars + 8 * (z < 4 ? B_Z + 2 * z + wg : B_HP + z - 4), 0, 8 + z);
        const uint8_t* src = smem + (z < 4 ? OFF_Z - z * U : z == 4 ? OFF_T : (z - 5) * U) + fo * 16;
#pragma unroll
        for (int i = 0; i < 4; i++) pv[i] = *(const uint4*)(src + i * 512);
      };
      auto check = [&](uint4 (&pv)[4], int z) {
#pragma unroll 1
        for (int n = 0; __any_sync(0xffffffffu, ((pv[0].x ^ tag) | (pv[1].x ^ tag) | (pv[2].x ^ tag) | (pv[3].x ^ tag)) & 1); n++) {
#pragma unroll
          for (int i = 0; i < 4; i++) pv[i] = ld_x4(ws->part + (size_t)((rb * 8 + j) * 3 + z - 4) * 1024 + fo + i * 32);
          if (n > (1 << 21)) __trap();
        }
#pragma unroll
        for (int i = 0; i < 4; i++) pv[i].x &= ~1u;
      };
      const uint32_t peerZ = mapa(sb + OFF_Z + fo * 16, rank ^ 1), peerB = mapa(bars + 8 * (B_Z + wg), rank ^ 1);
      auto tile_mma = [&](auto off, int t, int k0, int k1, int init) {
        constexpr int O = decltype(off)::value;
        const uint64_t db = d128(dN + (t & 3) * (TB >> 4)), dw = db + rank * 256, dm = db + (rank ? 0 : 1536);
#pragma unroll
        for (int k = k0; k < k1; k++) {
          if (k == 0) mma_rs64<O, 1, 2>(ct, h[0], h[1], h[2], h[3], dw, init);
          else if (k < 14) mma_rs64<O, 1, 1>(ct, h[4 * k], h[4 * k + 1], h[4 * k + 2], h[4 * k + 3], k < 12 ? dw + k * 128 : dm + (k - 12) * 128);
          else mma_rs64<O, 1, 1>(ct, yf[4 * k - 56], yf[4 * k - 55], yf[4 * k - 54], yf[4 * k - 53], db + k * 128);
        }
      };
      uint4 pv[4] = {};
      auto tile = [&](auto off, int t) {
        constexpr int P = 32 - decltype(off)::value;
        const bool grid = t >= 4 && t < 7, pre = t >= 3 && t != 6;
        const int zo = grid ? t - 4 : t == 7 ? 3 : t - 1, z = t - 3;
        const int owner = rb * 8 + 2 * ((q4 + zo + 1) & 3) + rank;
        uint4* dst = ws->part + (size_t)(owner * 3 + zo) * 1024 + fo;
        const uint32_t src = sb + (z < 4 ? OFF_Z - z * U : OFF_T) + fo * 16;
        twait(bars + 8 * (B_FT + (t & 3)), t >> 2, t);
        wg_fence();
        tile_mma(off, t, 0, TH, zero);
        wg_commit();
        wg_wait<1>();
        mbar_arrive_if(elect && t < 6, bars + 8 * (B_ET + t - 1));
        if (t < 3) twait(bars + 8 * (t == 1 ? B_RD0 : B_RDY), 0, 14 + t);
        fence_regs<P, 32>(ct);
#pragma unroll
        for (int i = 0; i < 4; i++) {
          pv[i].x = (add_bf2(pv[i].x, pack_bf16(ct[P + 8 * i], ct[P + 8 * i + 1])) & ~(uint32_t)grid) | (tag & grid);
          pv[i].y = add_bf2(pv[i].y, pack_bf16(ct[P + 8 * i + 2], ct[P + 8 * i + 3]));
          pv[i].z = add_bf2(pv[i].z, pack_bf16(ct[P + 8 * i + 4], ct[P + 8 * i + 5]));
          pv[i].w = add_bf2(pv[i].w, pack_bf16(ct[P + 8 * i + 6], ct[P + 8 * i + 7]));
        }
        if (grid) {
#pragma unroll
          for (int i = 0; i < 4; i++)
            asm volatile("st.relaxed.gpu.global.v4.u32 [%0], {%1,%2,%3,%4};" ::"l"(dst + i * 32), "r"(pv[i].x), "r"(pv[i].y), "r"(pv[i].z), "r"(pv[i].w) : "memory");
          hint_add_if(lane == 0, &ws->cntP[32 * owner + 8 * zo]);
        }
        auto share = [&](int i) {
          asm volatile("st.async.weak.shared::cluster.mbarrier::complete_tx::bytes.v4.b32 [%0], {%2,%3,%4,%5}, [%1];" ::"r"(peerZ - zo * U + i * 512),
                       "r"(peerB + 16 * zo), "r"(pv[i].x), "r"(pv[i].y), "r"(pv[i].z), "r"(pv[i].w) : "memory");
        };
        if (P == 0 && t == 7) { share(1); share(2); share(3); }
#pragma unroll
        for (int i = 0; i < 4; i++) {
          if (i == 0 ? !grid : t < 4) share(i);
          wg_fence();
          tile_mma(off, t, TH + SPC * i, i < 3 ? TH + SPC * i + SPC : TL, 0);
        }
        wg_commit();
        if (pre) twait(bars + 8 * (z < 4 ? B_Z + 2 * z + wg : B_HP), 0, 8 + z);
        wg_fence();
#pragma unroll
        for (int i = 0; i < 4; i++) {
          asm volatile("{\n.reg .pred p;\nsetp.ne.b32 p, %5, 0;\nmov.b32 %0, 0;\nmov.b32 %1, 0;\nmov.b32 %2, 0;\nmov.b32 %3, 0;\n@p ld.shared.v4.u32 {%0,%1,%2,%3}, [%4];\n}"
                       : "=r"(pv[i].x), "=r"(pv[i].y), "=r"(pv[i].z), "=r"(pv[i].w) : "r"(src + i * 512), "r"((int)pre) : "memory");
          tile_mma(off, t, TL + i, i < 3 ? TL + 1 + i : 18, 0);
        }
        wg_commit();
      };
      asm volatile("barrier.cluster.wait.aligned;" ::: "memory");
      twait(bars + 8 * B_FT, 0, 0);
      wg_fence();
      tile_mma(IC<0>(), 0, 0, T0A, zero);
      wg_commit();
      waitA(29 + wg);
      wg_wait<1>();
      mbar_arrive_if(elect, bars + 8 * (B_ET + 3));
      glu(cC, 32, 32, 0, 16);
      if (tid == 0) PROF_EV(6);
      if (tid == 128) PROF_EV(27);
      mbar_wait(bars + 8 * (j == 0 ? B_T : B_TL), 0);
      if (tid == 0) { PROF_EV(7); PROF_CK(45); }
      wg_fence();
      {
        const uint64_t dt = d128(dN + (OFF_T >> 4) + wg * 512), de = d128(dK + RING + (1 + wg) * 1024);
        mma_ss64<0, 1, 0>(ci, de, dt);
        mma_ss64<32, 1, 0>(ci, de + 512, dt);
#pragma unroll
        for (int k = 1; k < 4; k++) {
          mma_ss64<0, 1, 1>(ci, de + k * 2, dt + k * 128);
          mma_ss64<32, 1, 1>(ci, de + (512 + k * 2), dt + k * 128);
        }
        wg_commit();
      }
      tile_mma(IC<0>(), 0, T0A, 14, 0);
      wg_commit();
      wg_wait<1>();
      if (elect) asm volatile("mbarrier.arrive.shared::cluster.b64 _, [%0];" ::"r"(mapa(bars + 8 * B_RDY, rank ^ 1)) : "memory");
      mbar_arrive_if(elect, bars + 8 * (B_PZ + 1));
      fence_regs<0, 64>(ci);
#pragma unroll
      for (int i = 0; i < 16; i++) {
        const float gg = ((i & 1) ? g1 : g0) * (2.0f / (2048.0f * 512.0f));
        if (i & 2) yf[i] = pack_pin((ci[2 * i] - ci[28 + 2 * i]) * gg, (ci[2 * i + 1] - ci[29 + 2 * i]) * gg);
        else yf[i] = pack_pin((ci[2 * i] + ci[36 + 2 * i]) * gg, (ci[2 * i + 1] + ci[37 + 2 * i]) * gg);
      }
      wg_fence();
      tile_mma(IC<0>(), 0, 14, 18, 0);
      wg_commit();
      if (tid == 0) PROF_EV(8);
      if (tid == 128) PROF_EV(28);
#pragma unroll 1
      for (int t = 1;; t += 2) {
        tile(IC<32>(), t);
        if (t == 7) break;
        tile(IC<0>(), t + 1);
      }
      if (tid == 0) { PROF_EV(9); PROF_CK(46); }
      if (tid == 128) PROF_EV(29);
      {
        uint4 p1[4], p2[4];
        auto acc4 = [&](uint4 (&d)[4], const uint4 (&a)[4]) {
#pragma unroll
          for (int i = 0; i < 4; i++) { d[i].x = add_bf2(d[i].x, a[i].x); d[i].y = add_bf2(d[i].y, a[i].y); d[i].z = add_bf2(d[i].z, a[i].z); d[i].w = add_bf2(d[i].w, a[i].w); }
        };
        fetch(p1, 5);
        fetch(p2, 3);
        if (tid == 0) PROF_EV(25);
        wg_wait<0>();
        fence_regs<32, 32>(ct);
        check(pv, 4); check(p1, 5);
        acc4(pv, p1); acc4(pv, p2);
#pragma unroll
        for (int i = 0; i < 4; i++) {
          pv[i].x = pack_pin(ct[32 + 8 * i] + bf_lo(pv[i].x), ct[33 + 8 * i] + bf_hi(pv[i].x)); pv[i].y = pack_pin(ct[34 + 8 * i] + bf_lo(pv[i].y), ct[35 + 8 * i] + bf_hi(pv[i].y));
          pv[i].z = pack_pin(ct[36 + 8 * i] + bf_lo(pv[i].z), ct[37 + 8 * i] + bf_hi(pv[i].z)); pv[i].w = pack_pin(ct[38 + 8 * i] + bf_lo(pv[i].w), ct[39 + 8 * i] + bf_hi(pv[i].w));
        }
        if (tid == 0) PROF_EV(14);
        fetch(p2, 6);
        if (tid == 0) PROF_EV(24);
        check(p2, 6);
        acc4(pv, p2);
        const uint32_t stg = sb + OFF_T + warp * 2048;
        const int mr = (lane & 7) + ((lane >> 3) & 1) * 8, mc = lane >> 4;
#pragma unroll
        for (int i = 0; i < 4; i++)
          asm volatile("stmatrix.sync.aligned.m8n8.x4.shared.b16 [%0], {%1,%2,%3,%4};" ::"r"(stg + mr * 128 + (((2 * i + mc) ^ (mr & 7)) << 4)), "r"(pv[i].x),
                       "r"(pv[i].y), "r"(pv[i].z), "r"(pv[i].w) : "memory");
        __syncwarp();
#pragma unroll
        for (int i = 0; i < 4; i++) {
          const int r = 4 * i + (lane >> 3), c = lane & 7;
          const uint4 v = *(const uint4*)(smem + OFF_T + warp * 2048 + r * 128 + ((c ^ (r & 7)) << 4));
          *(uint4*)(out + (size_t)(2 * rb + wg + 32 * (16 * w + r)) * 512 + 64 * j + 8 * c) = v;
        }
      }
      if (tid == 0) { PROF_EV(15); PROF_CK(41); }
      if (tid == 128) PROF_EV(30);
    }
  } else if (warp < 12) {
    asm volatile("setmaxnreg.dec.sync.aligned.u32 104;");
    asm volatile("barrier.cluster.arrive.relaxed.aligned;" ::: "memory");
    const int t = tid - 256, w = warp - 8;
    const uint32_t ep = ld_x1(&ws->epoch[blockIdx.x * 8]);
    const uint32_t tag = (ep + 1) & 1;
    auto w_issue = [&](const CUtensorMap* m) {

      if (elect_one()) { mbar_expect_tx(bars + 8 * (B_WR + w), 3072); tma4d(sb + OFF_T + w * 3072, m, bars + 8 * (B_WR + w), 16 * kg, 0, 2 * w, tn); }

          __syncwarp();
    };
    auto gate_rows = [&] {
      const int r = 16 * j + 4 * w + (lane >> 3);
      const uint4* pg = (const uint4*)gate_w + (lane & 7);
      {
        float a = 0.f;
        asm volatile("bar.sync 4, 256;" ::: "memory");
#pragma unroll 1
        for (int hf = 0; hf < 2; hf++) {
          uint4 v[4], u[4];
#pragma unroll
          for (int kb = 0; kb < 4; kb++) v[kb] = __ldg(pg + (4 * hf + kb) * 8);
          mbar_wait(bars + 8 * (B_FE + 1 + 2 * hf), 0);
          if (hf) w_issue(&maps.wr);
#pragma unroll
          for (int kb = 0; kb < 4; kb++) u[kb] = *(const uint4*)(smem + (4 * hf + kb) * U + r * 128 + (((lane ^ r) & 7) << 4));
#pragma unroll
          for (int kb = 0; kb < 4; kb++) {
            const uint32_t uu[4] = {u[kb].x, u[kb].y, u[kb].z, u[kb].w}, vv[4] = {v[kb].x, v[kb].y, v[kb].z, v[kb].w};
#pragma unroll
            for (int e = 0; e < 4; e++) {
              uint32_t pr;
              asm("mul.rn.bf16x2 %0, %1, %2;" : "=r"(pr) : "r"(uu[e]), "r"(vv[e]));
              a += bf_lo(pr) + bf_hi(pr);
            }
          }
        }
#pragma unroll
        for (int o = 4; o; o >>= 1) a += __shfl_xor_sync(0xffffffffu, a, o);
        if ((lane & 7) == 0)
          asm volatile("st.relaxed.gpu.global.u32 [%0], %1;" ::"l"(ws->gate + rb * 128 + r),
                       "r"(pack_bf16(0.f, __fdividef(1.0f, 1.0f + __expf(-bf_lo(pack_bf16(a, 0.f))))) | tag) : "memory");
        if (t == 0) PROF_EV(18);
      }
    };
    {
      const int g = lane >> 2, q = lane & 3;
      uint32_t wf[32];
      if (!helper) {
        gate_rows();
        const uint32_t wa = sb + OFF_T + w * (3072 + 4) + q * 48 + g * 2;
#pragma unroll 1
        for (int ri = 0; ri < 2; ri++) {
          mbar_wait(bars + 8 * (B_WR + w), ri);
#pragma unroll
          for (int n2 = 0; n2 < 32 / WB; n2++) {
            uint32_t v[WB];
#pragma unroll
            for (int i = 0; i < WB; i++) {
              const int e = n2 * WB + i;
              asm volatile("ld.shared.u16 %0, [%1];" : "=r"(v[i]) : "r"(wa + ((e >> 1) & 7) * 192 + (e & 1) * (1536 + 2) + (e >> 4) * 16) : "memory");
            }
#pragma unroll
            for (int i = 0; i < WB; i++) wf[n2 * WB + i] = __byte_perm(wf[n2 * WB + i], v[i], 0x5432);
            if (WSLEEP) { asm volatile("nanosleep.u32 %0;" ::"r"(WSLEEP + (v[WB - 1] >> 16)) : "memory"); }
          }
          __syncwarp();
          if (ri == 0) w_issue(&maps.wi);
        }
        asm volatile("bar.sync 1, 128;" ::: "memory");
        if (t == 0) PROF_EV(11);
      } else {
        asm volatile("bar.sync 4, 256;" ::: "memory");
        hint_wait(&ws->cntW[0], (ep + 1) * 128u);
        const uint32_t t0 = (uint32_t)clock();
#pragma unroll 1
        for (;;) {
          uint32_t bad = 0;
#pragma unroll
          for (int i = 0; i < 32; i++) {
            const float2 v = ld_x2((const float2*)ws->Wh + (i >> 4) * 2048 + 16 * w + g + 8 * (i & 1) + 64 * q + ((i >> 1) & 7) * 256);
            wf[i] = __float_as_uint(v.x); bad |= __float_as_uint(v.y) ^ tag;
          }
          if (!__any_sync(0xffffffffu, bad & 1)) break;
          spin_guard(t0);
        }
        if (t == 0) PROF_EV(11);
      }
      if (w == 0 && elect_one()) { mbar_expect_tx(bars + 8 * B_W, 8192); bulk_load(sb + OFF_D, dtab, 8192, bars + 8 * B_W); }
      asm volatile("barrier.cluster.wait.aligned;" ::: "memory");
      mbar_wait(bars + 8 * B_W, 0);
      mbar_wait(bars + 8 * B_HX, 0);
      if (t == 0) PROF_EV(12);
      const uint32_t dd = (sb & 0x3FFFF) >> 4;
      const uint64_t dF = d128((dd + (OFF_D >> 4)) | (512u << 16)), dI = d128((dd + (OFF_D >> 4)) | (1u << 16)), dA = d128((dd + (OFF_XB >> 4)) | (512u << 16));
      float az[32];
      const int zero = blockIdx.x >> 16;
      uint32_t pf[32];
#pragma unroll
      for (int mt = 0; mt < 2; mt++) {
        wg_fence();
        if (mt == 0) mma_ss64<0, 3, 0>(az, dA, dF);
        else mma_ss64<0, 3, 2>(az, dA + 512, dF, zero);
#pragma unroll
        for (int k = 1; k < 4; k++) mma_ss64<0, 3, 1>(az, dA + (mt * 512 + k * 128), dF + k * 128);
        wg_commit();
        wg_wait<0>();
        fence_regs<0, 32>(az);
#pragma unroll
        for (int i = 0; i < 16; i++) {
          const float wr = bf_lo(wf[16 * mt + i]), wi = bf_hi(wf[16 * mt + i]);
          pf[16 * mt + i] = pack_pin(fmaf(az[2 * i], wr, -az[2 * i + 1] * wi), fmaf(az[2 * i], wi, az[2 * i + 1] * wr));
        }
      }
      if (t == 0) PROF_EV(16);
      {
        const int m = lane >> 3, r = lane & 7;
        const int sl = 2 * (m >> 1) + ((r >> 1) & 1) + 4 * (r >> 2);
        const uint32_t a0 = sb + OFF_XB + (2 * w + (m & 1)) * 2048 + sl * 64;
        uint32_t pk[16];
#pragma unroll
        for (int mt = 0; mt < 3; mt++) {
          if (mt < 2) {
            wg_fence();
            mma_rs64<0, 0, 2>(az, pf[16 * mt], pf[16 * mt + 1], pf[16 * mt + 2], pf[16 * mt + 3], dI, mt ? (int)helper : zero);
#pragma unroll
            for (int k = 1; k < 4; k++) mma_rs64<0, 0, 1>(az, pf[16 * mt + 4 * k], pf[16 * mt + 4 * k + 1], pf[16 * mt + 4 * k + 2], pf[16 * mt + 4 * k + 3], dI + k * 2);
            wg_commit();
          }
          if (mt > 0 && !helper) {
#pragma unroll
            for (int i = 0; i < 4; i++) stsm4t(a0 + ((((mt - 1) * 2 + (r & 1)) ^ (sl >> 1)) << 4) + i * 512, pk[4 * i], pk[4 * i + 1], pk[4 * i + 2], pk[4 * i + 3]);
          }
          if (mt < 2) {
            wg_wait<0>();
            fence_regs<0, 32>(az);
#pragma unroll
            for (int i = 0; i < 16; i++) pk[i] = pack_pin(az[2 * i], az[2 * i + 1]);
          }
        }
      }
      if (helper) {
#pragma unroll
        for (int i = 0; i < 16; i++) {
          const int n = i >> 1, s0 = 8 * (n >> 1) + 2 * (n & 1) + (q & 1) + 4 * (q >> 1);
          if ((n & 1) == (int)(blockIdx.x & 1)) st_u2(ws->Ts + s0 * 64 + 16 * w + g + 8 * (i & 1), pack_bf16(az[2 * i], az[2 * i + 1]), tag);
        }
        __syncwarp();
        hint_add_if(lane == 0, &ws->cntH[0]);
        if (t == 0) { ws->epoch[blockIdx.x * 8] = ep + 1; PROF_EV(13); }
      } else {
        asm volatile("fence.proxy.async.shared::cta;" ::: "memory");
        __syncwarp();
        if (elect_one()) {
          if (t == 0) PROF_EV(17);
          if (SPACE) __nanosleep(SPACE * w);
          asm volatile("cp.async.bulk.tensor.3d.global.shared::cta.bulk_group [%0, {%2, %3, %4}], [%1];" ::"l"(&maps.ts), "r"(sb + OFF_XB + w * 4096),
                       "r"(32 * kg), "r"(0), "r"(8 * tn + 2 * w) : "memory");
          bulk_done_signal(&ws->cntT[32 * j]);
          asm volatile("mbarrier.arrive.shared::cluster.b64 _, [%0];" ::"r"(mapa(bars + 8 * B_RD0, rank ^ 1)) : "memory");
          if (t == 96) PROF_EV(13);
        }
        __syncwarp();
        if (j == 0) {
          hint_wait(&ws->cntH[0], (ep + 1) * 8u);
          const uint32_t t0 = (uint32_t)clock();
          float2 v;
          do { v = ld_x2((const float2*)ws->Ts + 2 * rb * 64 + t); spin_guard(t0); } while (__any_sync(0xffffffffu, (__float_as_uint(v.y) ^ tag) & 1));
          mbar_wait(bars + 8 * B_TL, 0);
          const uint32_t u = __float_as_uint(v.x);
          *(uint16_t*)(smem + OFF_T + t * 128 + ((t & 7) << 4)) = (uint16_t)u;
          *(uint16_t*)(smem + OFF_T + t * 128 + (((t & 7) ^ 1) << 4)) = (uint16_t)(u >> 16);
          asm volatile("fence.proxy.async.shared::cta;" ::: "memory");
          __syncwarp();
          mbar_arrive_if(lane == 0, bars + 8 * B_T);
        }
      }
    }
  } else {
    asm volatile("setmaxnreg.dec.sync.aligned.u32 24;");
    auto xf_load = [&](int q) {
      const uint32_t fb = bars + 8 * (B_FX + q);
      mbar_expect_tx(fb, U + 8192);
      tma3d(sb + q * U, &maps.x, fb, 64 * q, 0, 2 * rb);
      if (q >= 4) mbar_wait(bars + 8 * (B_FE + ((q - 4) >> 1)), 0);
      tma2d(sb + OFF_XB + (q & 3) * 8192, &maps.ft, fb, 64 * q, 64 * j);
    };
    if (elect_one()) {
      if (warp == 14) {
#pragma unroll
        for (int i = 0; i < B_FT; i++) mbar_init(bars + 8 * i, 1);
        asm volatile("fence.mbarrier_init.release.cluster;" ::: "memory");
        if (!helper) {
#pragma unroll 1
          for (int n = 0; n < 2; n++) {
            const uint32_t fb = bars + 8 * (B_FA + n);
            xf_load(2 * n); xf_load(2 * n + 1);
            mbar_expect_tx(fb, U);
            tma2d(sb + OFF_RING + n * U, &maps.g64, fb, f_full, 64 * n);
            tma2d(sb + OFF_RING + n * U + 8192, &maps.u64, fb, f_full, 64 * n);
          }
        }
      } else if (warp == 15) {
#pragma unroll
        for (int i = B_FT; i < NBAR; i++) mbar_init(bars + 8 * i, i < B_EA ? 1 : i < B_T ? 2 : 4);
#pragma unroll
        for (int i = 0; i < 8; i++) mbar_expect_tx(bars + 8 * (B_Z + i), U / 2);
        asm volatile("fence.mbarrier_init.release.cluster;" ::: "memory");
        asm volatile("fence.proxy.async.shared::cta;" ::: "memory");
      }
    }
    __syncwarp();
    asm volatile("bar.arrive 0, 384;" ::: "memory");
    asm volatile("bar.arrive 4, 256;" ::: "memory");
    __syncwarp();
    asm volatile("barrier.cluster.arrive.relaxed.aligned;" ::: "memory");
    asm volatile("bar.sync 3, 128;" ::: "memory");
    if (warp == 15 && !helper) {
        mbar_wait(bars + 8 * B_FE, 0);
        const uint32_t tag = (ld_x1(&ws->epoch[blockIdx.x * 8]) + 1) & 1;
        const int c = lane >> 4, jj = 16 * blockIdx.x + (lane & 15), jm = (2048 - jj) & 2047;
        const unsigned short* pr = (const unsigned short*)w_r + 256 * c;
        const unsigned short* pi = (const unsigned short*)w_i + 256 * c;
        const float wr = 0.25f * (bf_lo(__ldg(pr + jj * 257)) + bf_lo(__ldg(pr + jm * 257)));
        const float wi = 0.25f * (bf_lo(__ldg(pi + jj * 257)) - bf_lo(__ldg(pi + jm * 257)));
        st_u2(ws->Wh + c * 2048 + jj, c ? pack_bf16(-wi, wr) : pack_bf16(wr, wi), tag);
        __syncwarp();
        hint_add_if(lane == 0, &ws->cntW[0]);
        mbar_wait(bars + 8 * B_XS, 0);
        const uint32_t t0 = (uint32_t)clock();
        uint4 v;
        do { v = ld_x4(ws->gate + rb * 128 + 4 * lane); spin_guard(t0); } while (__any_sync(0xffffffffu, ((v.x ^ tag) | (v.y ^ tag) | (v.z ^ tag) | (v.w ^ tag)) & 1));
        *(uint4*)(smem + OFF_G + lane * 16) = v;
        __syncwarp();
        mbar_arrive_if(lane < 4, bars + 8 * B_G);
      }
    auto part_load = [&](int i, unsigned ep1) {
      flag_wait(&ws->cntP[32 * (rb * 8 + j) + 8 * i], ep1 * 8u);
      mbar_wait(bars + 8 * (B_PZ + (i == 0)), 0);
      if (i == 2) PROF_EV(26);
      mbar_expect_tx(bars + 8 * (B_HP + i), U);
      bulk_load(sb + (i ? (i - 1) * U : OFF_T), ws->part + (size_t)((rb * 8 + j) * 3 + i) * 1024, U, bars + 8 * (B_HP + i));
    };
    if ((!helper || warp == 15) && elect_one()) {
      if (warp < 14) {
        const int p = warp - 12;
#pragma unroll 1
        for (int i = 4 + p; i < 13; i += 2) asm volatile("prefetch.tensormap [%0];" ::"l"((const char*)&maps + i * 128) : "memory");
#pragma unroll 1
        for (int n = 2; n < 31; n++) {
          const bool table = n == 4 || n >= 29;
          const bool half = n >= 17 && n < 21;
          const int q = n < 4 ? n : n < 17 ? n - 1 : n - 5;
          const CUtensorMap* m = table ? &maps.e : half ? &maps.g32 + p : &maps.g64 + p;
          const int c0 = table ? 0 : half ? f_half : f_full + 64 * (q >> 3);
          const int c1 = table ? (2 * rb + ((n & 1) ^ 1)) * 128 + 64 * p : half ? 128 * (n - 17) : 64 * (q & 7);
          const uint32_t fb = bars + 8 * (B_FA + (n & 3)), dst = sb + OFF_RING + (n & 3) * U + p * 8192;
          if (n < 4) mbar_wait(bars + 8 * (B_FE + n - 2), 0);
          else mbar_wait(bars + 8 * (B_EA + (n & 3)), ((n >> 2) & 1) ^ 1);
          tma2d(dst, m, fb, c0, c1);
          if (p == 0) mbar_expect_tx(fb, U);
        }
        mbar_wait(bars + 8 * (B_PZ + 1), 0);
        part_load(1 + p, ld_x1(&ws->epoch[blockIdx.x * 8]) + 1);
      } else if (warp == 15) {
        const unsigned ep1 = ld_x1(&ws->epoch[blockIdx.x * 8]) + 1;
        flag_wait(&ws->cntX[helper ? 0 : 32 * j], ep1 * 16u);
        PROF_EV(22);
        mbar_expect_tx(bars + 8 * B_HX, U);
        bulk_load(sb + OFF_XB, ws->X + (size_t)(helper ? 128 : kg * 8 + tn) * 8192, U, bars + 8 * B_HX);
        if (!helper) {
          flag_wait(&ws->cntT[32 * j], ep1 * 64u);
          PROF_EV(23);
          mbar_expect_tx(bars + 8 * B_TL, U);
          tma3d(sb + OFF_T, &maps.t, bars + 8 * B_TL, 64 * j, 0, 2 * rb);
          part_load(0, ep1);
          mbar_wait(bars + 8 * (B_HP + 1), 0); mbar_wait(bars + 8 * (B_HP + 2), 0);
          ws->epoch[blockIdx.x * 8] = ep1;
        }
      } else {
#pragma unroll 1
        for (int q = 4; q < 8; q++) xf_load(q);
        mbar_wait(bars + 8 * (B_FE + 2), 0);
        mbar_expect_tx(bars + 8 * B_E0, U);
        tma2d(sb + OFF_XB, &maps.e, bars + 8 * B_E0, 0, 2 * rb * 128);
        tma2d(sb + OFF_XB + 8192, &maps.e, bars + 8 * B_E0, 0, 2 * rb * 128 + 64);
#pragma unroll 1
        for (int h2 = 0; h2 < 2; h2++) {
          const int s0 = 2 * rb + h2, sg = (s0 & ~6) | ((s0 & 2) << 1) | ((s0 & 4) >> 1);
          mbar_wait(bars + 8 * (B_XS + h2), 0);
#pragma unroll 1
          for (int c = 0; c < 2; c++) {
            asm volatile("cp.async.bulk.tensor.4d.global.shared::cta.bulk_group [%0, {%2, %3, %4, %5}], [%1];" ::"l"(&maps.xs),
                         "r"(sb + OFF_XB + h2 * 8192 + c * 4096), "r"(0), "r"(sg), "r"(0), "r"(16 * j + 8 * c) : "memory");
            if (j == 0)
              asm volatile("cp.async.bulk.global.shared::cta.bulk_group [%0], [%1], 256;" ::"l"(ws->X + 128 * 8192 + c * 4096 + sg * 128),
                           "r"(sb + OFF_SP + h2 * 512 + c * 256) : "memory");
            if (SPACE && h2 + c < 2) __nanosleep(SPACE);
          }
        }
        bulk_done_signal(&ws->cntX[32 * j]);
        PROF_EV(20);
#pragma unroll 1
        for (int t = 0; t < 8; t++) {
          const int i = t < 3 ? t + 1 : t < 6 ? t - 2 : 0;
          const int col = 64 * (2 * ((q4 + i) & 3) + ((t < 3 || t == 6) ? 1 - rank : rank));
          const uint32_t fb = bars + 8 * (B_FT + (t & 3)), dst = sb + (t & 3) * TB;
          mbar_wait(bars + 8 * (B_ET + (t == 2 ? 3 : t & 3)), t >> 2);
          mbar_expect_tx(fb, TB);
          tma2d(dst, &maps.d224, fb, col, 224 * j);
          if (t < 2) mbar_wait(bars + 8 * (B_ET + t + 1), 0);
          tma2d(dst + 28672, &maps.ft, fb, col, 64 * j);
        }
      }
    }
  }
}

typedef CUresult (*EncodeFn)(CUtensorMap*, CUtensorMapDataType, cuuint32_t, void*, const cuuint64_t*, const cuuint64_t*, const cuuint32_t*,
                             const cuuint32_t*, CUtensorMapInterleave, CUtensorMapSwizzle, CUtensorMapL2promotion, CUtensorMapFloatOOBfill);

static void encode(EncodeFn f, CUtensorMap* m, const void* base, int rank, const cuuint64_t* dims, const cuuint64_t* strides, const cuuint32_t* box,
                   CUtensorMapSwizzle sw) {
  cuuint32_t es[5] = {1, 1, 1, 1, 1};
  f(m, CU_TENSOR_MAP_DATA_TYPE_BFLOAT16, rank, (void*)base, dims, strides, box, es, CU_TENSOR_MAP_INTERLEAVE_NONE, sw,
    CU_TENSOR_MAP_L2_PROMOTION_L2_128B, CU_TENSOR_MAP_FLOAT_OOB_FILL_NONE);
}

extern "C" void kernel_launch(void* const* d_in, const int* in_sizes, int n_in, void* d_out, int out_size) {
  (void)in_sizes; (void)n_in; (void)out_size;
  const __nv_bfloat16* x = (const __nv_bfloat16*)d_in[0];
  const __nv_bfloat16* w_r = (const __nv_bfloat16*)d_in[1];
  const __nv_bfloat16* w_i = (const __nv_bfloat16*)d_in[2];
  const __nv_bfloat16* Wg = (const __nv_bfloat16*)d_in[4];
  const __nv_bfloat16* Wu = (const __nv_bfloat16*)d_in[5];
  const __nv_bfloat16* Wd = (const __nv_bfloat16*)d_in[6];
  const __nv_bfloat16* gw = (const __nv_bfloat16*)d_in[7];

  void* fp = nullptr; cudaDriverEntryPointQueryResult qr;
  cudaGetDriverEntryPoint("cuTensorMapEncodeTiled", &fp, cudaEnableDefault, &qr);
  EncodeFn enc = (EncodeFn)fp;
  void *pFT, *pET, *pDT, *pW;
  cudaGetSymbolAddress(&pDT, g_DT); cudaGetSymbolAddress(&pW, g_work);
  void *pX = ((Work*)pW)->X, *pT = ((Work*)pW)->T;
  cudaGetSymbolAddress(&pFT, g_FT); cudaGetSymbolAddress(&pET, g_ET);

  Maps mp;
  const CUtensorMapSwizzle S128 = CU_TENSOR_MAP_SWIZZLE_128B, S64 = CU_TENSOR_MAP_SWIZZLE_64B;
  { cuuint64_t d[3] = {512, 64, 32}, s[2] = {32768, 1024}; cuuint32_t b[3] = {64, 64, 2}; encode(enc, &mp.x, x, 3, d, s, b, S128); }
  { cuuint64_t d[2] = {512, 512}, s[1] = {1024}; cuuint32_t b[2] = {64, 64}; encode(enc, &mp.ft, pFT, 2, d, s, b, S128); }
  { cuuint64_t d[4] = {128, 32, 2, 129}, s[3] = {256, 8192, 16384}; cuuint32_t b[4] = {128, 1, 2, 8}; encode(enc, &mp.xs, pX, 4, d, s, b, CU_TENSOR_MAP_SWIZZLE_NONE); }
  { cuuint64_t d[3] = {512, 32, 64}, s[2] = {65536, 1024}; cuuint32_t b[3] = {32, 32, 2}; encode(enc, &mp.ts, pT, 3, d, s, b, S64); }
  { cuuint64_t d[3] = {512, 64, 32}, s[2] = {1024, 65536}; cuuint32_t b[3] = {64, 64, 2}; encode(enc, &mp.t, pT, 3, d, s, b, S128); }
  { cuuint64_t d[2] = {64, 4096}, s[1] = {128}; cuuint32_t b[2] = {64, 64}; encode(enc, &mp.e, pET, 2, d, s, b, S128); }
  { cuuint64_t d[2] = {1792, 512}, s[1] = {3584}; cuuint32_t b[2] = {64, 64}, b2[2] = {32, 128};
    encode(enc, &mp.g64, Wg, 2, d, s, b, S128); encode(enc, &mp.u64, Wu, 2, d, s, b, S128);
    encode(enc, &mp.g32, Wg, 2, d, s, b2, S64); encode(enc, &mp.u32, Wu, 2, d, s, b2, S64); }
  { cuuint64_t d[2] = {512, 1792}, s[1] = {1024}; cuuint32_t b[2] = {64, 224}; encode(enc, &mp.d224, Wd, 2, d, s, b, S128); }
  { cuuint64_t d[4] = {264, 32, 8, 8}, s[3] = {32896, 512, 4112}; cuuint32_t b[4] = {24, 32, 2, 1};
    encode(enc, &mp.wr, w_r, 4, d, s, b, CU_TENSOR_MAP_SWIZZLE_NONE); encode(enc, &mp.wi, w_i, 4, d, s, b, CU_TENSOR_MAP_SWIZZLE_NONE); }

  cudaFuncSetAttribute(fused_kernel, cudaFuncAttributeMaxDynamicSharedMemorySize, SMEM_BYTES);
  fused_kernel<<<NCTA, 512, SMEM_BYTES>>>((Work*)pW, (const uint16_t*)pDT, w_r, w_i, gw, x, (__nv_bfloat16*)d_out, mp);
}
```

```cpp
#include <cuda_runtime.h>
#include <cuda_bf16.h>
#include <cuda.h>
#include <stdint.h>

namespace tbl {
constexpr double PI = 3.14159265358979323846264338327950288;
constexpr double sin_s(double x) { double t = x, s = x; for (int n = 1; n < 12; n++) { t *= -x * x / ((2 * n) * (2 * n + 1)); s += t; } return s; }
constexpr double cos_s(double x) { double t = 1, s = 1; for (int n = 1; n < 12; n++) { t *= -x * x / ((2 * n - 1) * (2 * n)); s += t; } return s; }
constexpr double cos2048(int m) {
  m &= 2047; if (m > 1024) m = 2048 - m;
  bool neg = false; if (m > 512) { m = 1024 - m; neg = true; }
  double v = (m <= 256) ? cos_s(2 * PI * m / 2048) : sin_s(2 * PI * (512 - m) / 2048);
  return neg ? -v : v;
}
constexpr uint16_t to_bf16(double v) {
  if (v == 0) return 0;
  uint16_t s = 0; if (v < 0) { s = 0x8000; v = -v; }
  int e = 0; while (v >= 2) { v /= 2; e++; } while (v < 1) { v *= 2; e--; }
  double m = (v - 1) * 128; int mi = (int)m; double fr = m - mi;
  if (fr > 0.5 || (fr == 0.5 && (mi & 1))) mi++;
  if (mi == 128) { mi = 0; e++; }
  return (uint16_t)(s | ((e + 127) << 7) | mi);
}
struct CosT { uint16_t v[2048]; constexpr CosT() : v() { for (int i = 0; i < 2048; i++) v[i] = to_bf16(cos2048(i)); } };
struct alignas(1024) FT {
  uint16_t v[512 * 512];
  constexpr FT() : v() {
    CosT c;
    for (int r = 0; r < 512; r++) {
      int k = (r >> 4) * 8 + (r & 7), e = (r >> 3) & 1;
      int mul = 4 * k, add = e ? 512 : 0;
      if (k == 0 && e == 1) { mul = 1024; add = 0; }
      for (int d = 0; d < 512; d++) v[r * 512 + d] = c.v[(d * mul + add) & 2047];
    }
  }
};
struct alignas(1024) ET {
  uint16_t v[2048 * 128];
  constexpr ET() : v() {
    CosT c;
    for (int s = 0; s < 2048; s++)
      for (int j = 0; j < 64; j++) {
        const int o = (s & 31) * 8192 + (s >> 5) * 64 + j;
        v[o] = c.v[(s * j) & 2047]; v[o + 4096] = c.v[(s * j + 512) & 2047];
      }
  }
};
struct alignas(1024) DT {
  uint16_t v[64 * 64];
  constexpr DT() : v() {
    CosT c;
    for (int r = 0; r < 64; r++)
      for (int n = 0; n < 64; n++) {
        const int sg = r >> 1, s0 = (sg & ~6) | ((sg & 2) << 1) | ((sg & 4) >> 1), e = r & 1, f = n & 1;
        const int m = 64 * s0 * (n >> 1) + (e == f ? 0 : e ? -512 : 512);
        v[r * 64 + (((n >> 3) ^ (r & 7)) << 3) + (n & 7)] = c.v[m & 2047];
      }
  }
};
}

__device__ constexpr tbl::FT g_FT = tbl::FT();
__device__ constexpr tbl::ET g_ET = tbl::ET();
__device__ constexpr tbl::DT g_DT = tbl::DT();

struct alignas(1024) Work {
  unsigned epoch[132 * 8];
  unsigned cntX[8 * 32], cntT[8 * 32], cntP[128 * 32], cntW[32], cntH[32];
  alignas(16) float gate[16 * 128];
  alignas(16) uint2 Wh[2 * 2048];
  alignas(16) uint2 Ts[32 * 64];
  alignas(1024) uint16_t X[129 * 8192];
  alignas(1024) uint16_t T[32 * 64 * 512];
  alignas(1024) uint4 part[128 * 3 * 1024];
};
__device__ Work g_work;
#define PROF_EV(i) do {} while (0)
#define PROF_CK(i) do {} while (0)

__device__ __forceinline__ uint32_t smem_u32(const void* p) { return (uint32_t)__cvta_generic_to_shared(p); }
__device__ __forceinline__ void mbar_init(uint32_t bar, uint32_t cnt) { asm volatile("mbarrier.init.shared::cta.b64 [%0], %1;" ::"r"(bar), "r"(cnt)); }
__device__ __forceinline__ void mbar_expect_tx(uint32_t bar, uint32_t bytes) { asm volatile("mbarrier.arrive.expect_tx.shared::cta.b64 _, [%0], %1;" ::"r"(bar), "r"(bytes) : "memory"); }
__device__ __forceinline__ void mbar_arrive(uint32_t bar) { asm volatile("mbarrier.arrive.shared::cta.b64 _, [%0];" ::"r"(bar) : "memory"); }
__device__ __forceinline__ bool elect_one() {
  uint32_t p;
  asm volatile("{\n.reg .pred p;\nelect.sync _|p, 0xffffffff;\nselp.u32 %0, 1, 0, p;\n}" : "=r"(p));
  return p;
}
__device__ __forceinline__ void mbar_arrive_if(bool p, uint32_t bar) {
  asm volatile("{\n.reg .pred p;\nsetp.ne.b32 p, %1, 0;\n@p mbarrier.arrive.shared::cta.b64 _, [%0];\n}" ::"r"(bar), "r"((int)p) : "memory");
}
__device__ __forceinline__ void hint_add_if(bool p, unsigned* a) {
  asm volatile("{\n.reg .pred p;\nsetp.ne.b32 p, %1, 0;\n@p red.relaxed.gpu.global.add.u32 [%0], 1;\n}" ::"l"(a), "r"((int)p) : "memory");
}
__device__ __forceinline__ bool mbar_try(uint32_t bar, uint32_t parity) {
  uint32_t ok;
  asm volatile("{\n.reg .pred p;\nmbarrier.test_wait.parity.shared::cta.b64 p, [%1], %2;\nselp.u32 %0, 1, 0, p;\n}" : "=r"(ok) : "r"(bar), "r"(parity) : "memory");
  return ok;
}
__device__ __forceinline__ void mbar_wait(uint32_t bar, uint32_t parity) {
  asm volatile(
      "{\n.reg .pred p;\n.reg .u32 n;\nmov.u32 n, 0;\n"
      "W_LOOP:\nmbarrier.try_wait.parity.shared::cta.b64 p, [%0], %1;\n@p bra W_DONE;\n"
      "add.u32 n, n, 1;\nsetp.lt.u32 p, n, 0x40000;\n@p bra W_LOOP;\ntrap;\nW_DONE:\n}" ::"r"(bar), "r"(parity) : "memory");
}
__device__ __forceinline__ void bulk_load(uint32_t dst, const void* src, uint32_t bytes, uint32_t bar) {
  asm volatile("cp.async.bulk.shared::cluster.global.mbarrier::complete_tx::bytes [%0], [%1], %2, [%3];" ::"r"(dst), "l"(src), "r"(bytes), "r"(bar) : "memory");
}
__device__ __forceinline__ void spin_guard(uint32_t t0) { if ((uint32_t)clock() - t0 > (1u << 30)) __trap(); }
__device__ __forceinline__ float2 ld_x2(const float2* p) { float2 v; asm volatile("ld.relaxed.gpu.global.v2.f32 {%0,%1}, [%2];" : "=f"(v.x), "=f"(v.y) : "l"(p) : "memory"); return v; }
__device__ __forceinline__ void st_u2(uint2* p, uint32_t a, uint32_t b) { asm volatile("st.relaxed.gpu.global.v2.u32 [%0], {%1,%2};" ::"l"(p), "r"(a), "r"(b) : "memory"); }
__device__ __forceinline__ uint32_t ld_x1(const void* p) { uint32_t v; asm volatile("ld.relaxed.gpu.global.u32 %0, [%1];" : "=r"(v) : "l"(p) : "memory"); return v; }
__device__ __forceinline__ uint4 ld_x4(const void* p) { uint4 v; asm volatile("ld.relaxed.gpu.global.v4.u32 {%0,%1,%2,%3}, [%4];" : "=r"(v.x), "=r"(v.y), "=r"(v.z), "=r"(v.w) : "l"(p) : "memory"); return v; }
__device__ __forceinline__ uint32_t mapa(uint32_t a, uint32_t cta) { uint32_t r; asm volatile("mapa.shared::cluster.u32 %0, %1, %2;" : "=r"(r) : "r"(a), "r"(cta)); return r; }
__device__ __forceinline__ void stsm4t(uint32_t a, uint32_t r0, uint32_t r1, uint32_t r2, uint32_t r3) {
  asm volatile("stmatrix.sync.aligned.m8n8.x4.trans.shared.b16 [%0], {%1,%2,%3,%4};" ::"r"(a), "r"(r0), "r"(r1), "r"(r2), "r"(r3) : "memory");
}
__device__ __forceinline__ void hint_add(unsigned* p) { asm volatile("red.relaxed.gpu.global.add.u32 [%0], 1;" ::"l"(p) : "memory"); }
__device__ __forceinline__ void hint_wait(const unsigned* p, unsigned target) {
  const uint32_t t0 = (uint32_t)clock();
  while ((int)(ld_x1(p) - target) < 0) spin_guard(t0);
}
__device__ __forceinline__ void bulk_done_signal(unsigned* p) {
  asm volatile("cp.async.bulk.commit_group;\ncp.async.bulk.wait_group 0;\nfence.proxy.async.global;" ::: "memory");
  hint_add(p);
}
__device__ __forceinline__ void flag_wait(const unsigned* p, unsigned target) {
  hint_wait(p, target);
  asm volatile("fence.proxy.async.global;" ::: "memory");
}
__device__ __forceinline__ void tma2d(uint32_t dst, const CUtensorMap* m, uint32_t bar, int c0, int c1) {
  asm volatile("cp.async.bulk.tensor.2d.shared::cluster.global.mbarrier::complete_tx::bytes [%0], [%1, {%3, %4}], [%2];" ::"r"(dst), "l"(m), "r"(bar), "r"(c0), "r"(c1) : "memory");
}
__device__ __forceinline__ void tma3d(uint32_t dst, const CUtensorMap* m, uint32_t bar, int c0, int c1, int c2) {
  asm volatile("cp.async.bulk.tensor.3d.shared::cluster.global.mbarrier::complete_tx::bytes [%0], [%1, {%3, %4, %5}], [%2];" ::"r"(dst), "l"(m), "r"(bar), "r"(c0), "r"(c1), "r"(c2) : "memory");
}
__device__ __forceinline__ void tma4d(uint32_t dst, const CUtensorMap* m, uint32_t bar, int c0, int c1, int c2, int c3) {
  asm volatile("cp.async.bulk.tensor.4d.shared::cluster.global.mbarrier::complete_tx::bytes [%0], [%1, {%3, %4, %5, %6}], [%2];" ::"r"(dst), "l"(m), "r"(bar), "r"(c0), "r"(c1), "r"(c2), "r"(c3) : "memory");
}
__device__ __forceinline__ void wg_fence() { asm volatile("wgmma.fence.sync.aligned;" ::: "memory"); }
__device__ __forceinline__ void wg_commit() { asm volatile("wgmma.commit_group.sync.aligned;" ::: "memory"); }
template <int N> __device__ __forceinline__ void wg_wait() { asm volatile("wgmma.wait_group.sync.aligned %0;" ::"n"(N) : "memory"); }
template <int O, int N, int NN> __device__ __forceinline__ void fence_regs(float (&d)[NN]) {
#pragma unroll
  for (int i = 0; i < N; i++) asm volatile("" : "+f"(d[O + i])::"memory");
}
__device__ __forceinline__ uint32_t pack_bf16(float lo, float hi) {
  uint32_t r; asm("cvt.rn.bf16x2.f32 %0, %1, %2;" : "=r"(r) : "f"(hi), "f"(lo)); return r;
}
__device__ __forceinline__ uint32_t pack_pin(float lo, float hi) {
  uint32_t r; asm volatile("cvt.rn.bf16x2.f32 %0, %1, %2;" : "=r"(r) : "f"(hi), "f"(lo) : "memory"); return r;
}
__device__ __forceinline__ uint32_t add_bf2(uint32_t a, uint32_t b) { uint32_t r; asm("add.rn.bf16x2 %0, %1, %2;" : "=r"(r) : "r"(a), "r"(b)); return r; }
__device__ __forceinline__ float bf_lo(uint32_t u) { return __uint_as_float(u << 16); }
__device__ __forceinline__ float bf_hi(uint32_t u) { return __uint_as_float(u & 0xffff0000u); }

__device__ __forceinline__ uint64_t d128(uint32_t lo) { uint64_t d; asm("mov.b64 %0, {%1, 0x40000040};" : "=l"(d) : "r"(lo)); return d; }
__device__ __forceinline__ uint64_t d64(uint32_t lo) { uint64_t d; asm("mov.b64 %0, {%1, 0x80000020};" : "=l"(d) : "r"(lo)); return d; }
template<int O,int TB,int ACC,int NN> __device__ __forceinline__ void mma_ss64(float (&d)[NN], uint64_t da, uint64_t db, int sd = 0){
  if constexpr (ACC == 1) asm volatile("wgmma.mma_async.sync.aligned.m64n64k16.f32.bf16.bf16 {%0,%1,%2,%3,%4,%5,%6,%7,%8,%9,%10,%11,%12,%13,%14,%15,%16,%17,%18,%19,%20,%21,%22,%23,%24,%25,%26,%27,%28,%29,%30,%31}, %32, %33, 1, 1, 1, %35, %34;"
   : "+f"(d[O+0]), "+f"(d[O+1]), "+f"(d[O+2]), "+f"(d[O+3]), "+f"(d[O+4]), "+f"(d[O+5]), "+f"(d[O+6]), "+f"(d[O+7]), "+f"(d[O+8]), "+f"(d[O+9]), "+f"(d[O+10]), "+f"(d[O+11]), "+f"(d[O+12]), "+f"(d[O+13]), "+f"(d[O+14]), "+f"(d[O+15]), "+f"(d[O+16]), "+f"(d[O+17]), "+f"(d[O+18]), "+f"(d[O+19]), "+f"(d[O+20]), "+f"(d[O+21]), "+f"(d[O+22]), "+f"(d[O+23]), "+f"(d[O+24]), "+f"(d[O+25]), "+f"(d[O+26]), "+f"(d[O+27]), "+f"(d[O+28]), "+f"(d[O+29]), "+f"(d[O+30]), "+f"(d[O+31])
   : "l"(da), "l"(db), "n"(TB & 1), "n"(TB >> 1));
  else if constexpr (ACC == 0) asm volatile("wgmma.mma_async.sync.aligned.m64n64k16.f32.bf16.bf16 {%0,%1,%2,%3,%4,%5,%6,%7,%8,%9,%10,%11,%12,%13,%14,%15,%16,%17,%18,%19,%20,%21,%22,%23,%24,%25,%26,%27,%28,%29,%30,%31}, %32, %33, 0, 1, 1, %35, %34;"
   : "=f"(d[O+0]), "=f"(d[O+1]), "=f"(d[O+2]), "=f"(d[O+3]), "=f"(d[O+4]), "=f"(d[O+5]), "=f"(d[O+6]), "=f"(d[O+7]), "=f"(d[O+8]), "=f"(d[O+9]), "=f"(d[O+10]), "=f"(d[O+11]), "=f"(d[O+12]), "=f"(d[O+13]), "=f"(d[O+14]), "=f"(d[O+15]), "=f"(d[O+16]), "=f"(d[O+17]), "=f"(d[O+18]), "=f"(d[O+19]), "=f"(d[O+20]), "=f"(d[O+21]), "=f"(d[O+22]), "=f"(d[O+23]), "=f"(d[O+24]), "=f"(d[O+25]), "=f"(d[O+26]), "=f"(d[O+27]), "=f"(d[O+28]), "=f"(d[O+29]), "=f"(d[O+30]), "=f"(d[O+31])
   : "l"(da), "l"(db), "n"(TB & 1), "n"(TB >> 1));
  else asm volatile("{\n.reg .pred p;\nsetp.ne.b32 p, %36, 0;\nwgmma.mma_async.sync.aligned.m64n64k16.f32.bf16.bf16 {%0,%1,%2,%3,%4,%5,%6,%7,%8,%9,%10,%11,%12,%13,%14,%15,%16,%17,%18,%19,%20,%21,%22,%23,%24,%25,%26,%27,%28,%29,%30,%31}, %32, %33, p, 1, 1, %35, %34;\n}"
   : "+f"(d[O+0]), "+f"(d[O+1]), "+f"(d[O+2]), "+f"(d[O+3]), "+f"(d[O+4]), "+f"(d[O+5]), "+f"(d[O+6]), "+f"(d[O+7]), "+f"(d[O+8]), "+f"(d[O+9]), "+f"(d[O+10]), "+f"(d[O+11]), "+f"(d[O+12]), "+f"(d[O+13]), "+f"(d[O+14]), "+f"(d[O+15]), "+f"(d[O+16]), "+f"(d[O+17]), "+f"(d[O+18]), "+f"(d[O+19]), "+f"(d[O+20]), "+f"(d[O+21]), "+f"(d[O+22]), "+f"(d[O+23]), "+f"(d[O+24]), "+f"(d[O+25]), "+f"(d[O+26]), "+f"(d[O+27]), "+f"(d[O+28]), "+f"(d[O+29]), "+f"(d[O+30]), "+f"(d[O+31])
   : "l"(da), "l"(db), "n"(TB & 1), "n"(TB >> 1), "r"(sd));
}
template<int O,int TB,int ACC,int NN> __device__ __forceinline__ void mma_rs64(float (&d)[NN], uint32_t a0, uint32_t a1, uint32_t a2, uint32_t a3, uint64_t db, int sd = 0){
  if constexpr (ACC == 1) asm volatile("wgmma.mma_async.sync.aligned.m64n64k16.f32.bf16.bf16 {%0,%1,%2,%3,%4,%5,%6,%7,%8,%9,%10,%11,%12,%13,%14,%15,%16,%17,%18,%19,%20,%21,%22,%23,%24,%25,%26,%27,%28,%29,%30,%31}, {%32,%33,%34,%35}, %36, 1, 1, 1, %37;"
   : "+f"(d[O+0]), "+f"(d[O+1]), "+f"(d[O+2]), "+f"(d[O+3]), "+f"(d[O+4]), "+f"(d[O+5]), "+f"(d[O+6]), "+f"(d[O+7]), "+f"(d[O+8]), "+f"(d[O+9]), "+f"(d[O+10]), "+f"(d[O+11]), "+f"(d[O+12]), "+f"(d[O+13]), "+f"(d[O+14]), "+f"(d[O+15]), "+f"(d[O+16]), "+f"(d[O+17]), "+f"(d[O+18]), "+f"(d[O+19]), "+f"(d[O+20]), "+f"(d[O+21]), "+f"(d[O+22]), "+f"(d[O+23]), "+f"(d[O+24]), "+f"(d[O+25]), "+f"(d[O+26]), "+f"(d[O+27]), "+f"(d[O+28]), "+f"(d[O+29]), "+f"(d[O+30]), "+f"(d[O+31])
   : "r"(a0), "r"(a1), "r"(a2), "r"(a3), "l"(db), "n"(TB));
  else if constexpr (ACC == 0) asm volatile("wgmma.mma_async.sync.aligned.m64n64k16.f32.bf16.bf16 {%0,%1,%2,%3,%4,%5,%6,%7,%8,%9,%10,%11,%12,%13,%14,%15,%16,%17,%18,%19,%20,%21,%22,%23,%24,%25,%26,%27,%28,%29,%30,%31}, {%32,%33,%34,%35}, %36, 0, 1, 1, %37;"
   : "=f"(d[O+0]), "=f"(d[O+1]), "=f"(d[O+2]), "=f"(d[O+3]), "=f"(d[O+4]), "=f"(d[O+5]), "=f"(d[O+6]), "=f"(d[O+7]), "=f"(d[O+8]), "=f"(d[O+9]), "=f"(d[O+10]), "=f"(d[O+11]), "=f"(d[O+12]), "=f"(d[O+13]), "=f"(d[O+14]), "=f"(d[O+15]), "=f"(d[O+16]), "=f"(d[O+17]), "=f"(d[O+18]), "=f"(d[O+19]), "=f"(d[O+20]), "=f"(d[O+21]), "=f"(d[O+22]), "=f"(d[O+23]), "=f"(d[O+24]), "=f"(d[O+25]), "=f"(d[O+26]), "=f"(d[O+27]), "=f"(d[O+28]), "=f"(d[O+29]), "=f"(d[O+30]), "=f"(d[O+31])
   : "r"(a0), "r"(a1), "r"(a2), "r"(a3), "l"(db), "n"(TB));
  else asm volatile("{\n.reg .pred p;\nsetp.ne.b32 p, %38, 0;\nwgmma.mma_async.sync.aligned.m64n64k16.f32.bf16.bf16 {%0,%1,%2,%3,%4,%5,%6,%7,%8,%9,%10,%11,%12,%13,%14,%15,%16,%17,%18,%19,%20,%21,%22,%23,%24,%25,%26,%27,%28,%29,%30,%31}, {%32,%33,%34,%35}, %36, p, 1, 1, %37;\n}"
   : "+f"(d[O+0]), "+f"(d[O+1]), "+f"(d[O+2]), "+f"(d[O+3]), "+f"(d[O+4]), "+f"(d[O+5]), "+f"(d[O+6]), "+f"(d[O+7]), "+f"(d[O+8]), "+f"(d[O+9]), "+f"(d[O+10]), "+f"(d[O+11]), "+f"(d[O+12]), "+f"(d[O+13]), "+f"(d[O+14]), "+f"(d[O+15]), "+f"(d[O+16]), "+f"(d[O+17]), "+f"(d[O+18]), "+f"(d[O+19]), "+f"(d[O+20]), "+f"(d[O+21]), "+f"(d[O+22]), "+f"(d[O+23]), "+f"(d[O+24]), "+f"(d[O+25]), "+f"(d[O+26]), "+f"(d[O+27]), "+f"(d[O+28]), "+f"(d[O+29]), "+f"(d[O+30]), "+f"(d[O+31])
   : "r"(a0), "r"(a1), "r"(a2), "r"(a3), "l"(db), "n"(TB), "r"(sd));
}
template<int O,int TB,int ACC,int NN> __device__ __forceinline__ void mma_ss128(float (&d)[NN], uint64_t da, uint64_t db, int sd = 0){
  if constexpr (ACC == 1) asm volatile("wgmma.mma_async.sync.aligned.m64n128k16.f32.bf16.bf16 {%0,%1,%2,%3,%4,%5,%6,%7,%8,%9,%10,%11,%12,%13,%14,%15,%16,%17,%18,%19,%20,%21,%22,%23,%24,%25,%26,%27,%28,%29,%30,%31,%32,%33,%34,%35,%36,%37,%38,%39,%40,%41,%42,%43,%44,%45,%46,%47,%48,%49,%50,%51,%52,%53,%54,%55,%56,%57,%58,%59,%60,%61,%62,%63}, %64, %65, 1, 1, 1, %67, %66;"
   : "+f"(d[O+0]), "+f"(d[O+1]), "+f"(d[O+2]), "+f"(d[O+3]), "+f"(d[O+4]), "+f"(d[O+5]), "+f"(d[O+6]), "+f"(d[O+7]), "+f"(d[O+8]), "+f"(d[O+9]), "+f"(d[O+10]), "+f"(d[O+11]), "+f"(d[O+12]), "+f"(d[O+13]), "+f"(d[O+14]), "+f"(d[O+15]), "+f"(d[O+16]), "+f"(d[O+17]), "+f"(d[O+18]), "+f"(d[O+19]), "+f"(d[O+20]), "+f"(d[O+21]), "+f"(d[O+22]), "+f"(d[O+23]), "+f"(d[O+24]), "+f"(d[O+25]), "+f"(d[O+26]), "+f"(d[O+27]), "+f"(d[O+28]), "+f"(d[O+29]), "+f"(d[O+30]), "+f"(d[O+31]), "+f"(d[O+32]), "+f"(d[O+33]), "+f"(d[O+34]), "+f"(d[O+35]), "+f"(d[O+36]), "+f"(d[O+37]), "+f"(d[O+38]), "+f"(d[O+39]), "+f"(d[O+40]), "+f"(d[O+41]), "+f"(d[O+42]), "+f"(d[O+43]), "+f"(d[O+44]), "+f"(d[O+45]), "+f"(d[O+46]), "+f"(d[O+47]), "+f"(d[O+48]), "+f"(d[O+49]), "+f"(d[O+50]), "+f"(d[O+51]), "+f"(d[O+52]), "+f"(d[O+53]), "+f"(d[O+54]), "+f"(d[O+55]), "+f"(d[O+56]), "+f"(d[O+57]), "+f"(d[O+58]), "+f"(d[O+59]), "+f"(d[O+60]), "+f"(d[O+61]), "+f"(d[O+62]), "+f"(d[O+63])
   : "l"(da), "l"(db), "n"(TB & 1), "n"(TB >> 1));
  else if constexpr (ACC == 0) asm volatile("wgmma.mma_async.sync.aligned.m64n128k16.f32.bf16.bf16 {%0,%1,%2,%3,%4,%5,%6,%7,%8,%9,%10,%11,%12,%13,%14,%15,%16,%17,%18,%19,%20,%21,%22,%23,%24,%25,%26,%27,%28,%29,%30,%31,%32,%33,%34,%35,%36,%37,%38,%39,%40,%41,%42,%43,%44,%45,%46,%47,%48,%49,%50,%51,%52,%53,%54,%55,%56,%57,%58,%59,%60,%61,%62,%63}, %64, %65, 0, 1, 1, %67, %66;"
   : "=f"(d[O+0]), "=f"(d[O+1]), "=f"(d[O+2]), "=f"(d[O+3]), "=f"(d[O+4]), "=f"(d[O+5]), "=f"(d[O+6]), "=f"(d[O+7]), "=f"(d[O+8]), "=f"(d[O+9]), "=f"(d[O+10]), "=f"(d[O+11]), "=f"(d[O+12]), "=f"(d[O+13]), "=f"(d[O+14]), "=f"(d[O+15]), "=f"(d[O+16]), "=f"(d[O+17]), "=f"(d[O+18]), "=f"(d[O+19]), "=f"(d[O+20]), "=f"(d[O+21]), "=f"(d[O+22]), "=f"(d[O+23]), "=f"(d[O+24]), "=f"(d[O+25]), "=f"(d[O+26]), "=f"(d[O+27]), "=f"(d[O+28]), "=f"(d[O+29]), "=f"(d[O+30]), "=f"(d[O+31]), "=f"(d[O+32]), "=f"(d[O+33]), "=f"(d[O+34]), "=f"(d[O+35]), "=f"(d[O+36]), "=f"(d[O+37]), "=f"(d[O+38]), "=f"(d[O+39]), "=f"(d[O+40]), "=f"(d[O+41]), "=f"(d[O+42]), "=f"(d[O+43]), "=f"(d[O+44]), "=f"(d[O+45]), "=f"(d[O+46]), "=f"(d[O+47]), "=f"(d[O+48]), "=f"(d[O+49]), "=f"(d[O+50]), "=f"(d[O+51]), "=f"(d[O+52]), "=f"(d[O+53]), "=f"(d[O+54]), "=f"(d[O+55]), "=f"(d[O+56]), "=f"(d[O+57]), "=f"(d[O+58]), "=f"(d[O+59]), "=f"(d[O+60]), "=f"(d[O+61]), "=f"(d[O+62]), "=f"(d[O+63])
   : "l"(da), "l"(db), "n"(TB & 1), "n"(TB >> 1));
  else asm volatile("{\n.reg .pred p;\nsetp.ne.b32 p, %68, 0;\nwgmma.mma_async.sync.aligned.m64n128k16.f32.bf16.bf16 {%0,%1,%2,%3,%4,%5,%6,%7,%8,%9,%10,%11,%12,%13,%14,%15,%16,%17,%18,%19,%20,%21,%22,%23,%24,%25,%26,%27,%28,%29,%30,%31,%32,%33,%34,%35,%36,%37,%38,%39,%40,%41,%42,%43,%44,%45,%46,%47,%48,%49,%50,%51,%52,%53,%54,%55,%56,%57,%58,%59,%60,%61,%62,%63}, %64, %65, p, 1, 1, %67, %66;\n}"
   : "+f"(d[O+0]), "+f"(d[O+1]), "+f"(d[O+2]), "+f"(d[O+3]), "+f"(d[O+4]), "+f"(d[O+5]), "+f"(d[O+6]), "+f"(d[O+7]), "+f"(d[O+8]), "+f"(d[O+9]), "+f"(d[O+10]), "+f"(d[O+11]), "+f"(d[O+12]), "+f"(d[O+13]), "+f"(d[O+14]), "+f"(d[O+15]), "+f"(d[O+16]), "+f"(d[O+17]), "+f"(d[O+18]), "+f"(d[O+19]), "+f"(d[O+20]), "+f"(d[O+21]), "+f"(d[O+22]), "+f"(d[O+23]), "+f"(d[O+24]), "+f"(d[O+25]), "+f"(d[O+26]), "+f"(d[O+27]), "+f"(d[O+28]), "+f"(d[O+29]), "+f"(d[O+30]), "+f"(d[O+31]), "+f"(d[O+32]), "+f"(d[O+33]), "+f"(d[O+34]), "+f"(d[O+35]), "+f"(d[O+36]), "+f"(d[O+37]), "+f"(d[O+38]), "+f"(d[O+39]), "+f"(d[O+40]), "+f"(d[O+41]), "+f"(d[O+42]), "+f"(d[O+43]), "+f"(d[O+44]), "+f"(d[O+45]), "+f"(d[O+46]), "+f"(d[O+47]), "+f"(d[O+48]), "+f"(d[O+49]), "+f"(d[O+50]), "+f"(d[O+51]), "+f"(d[O+52]), "+f"(d[O+53]), "+f"(d[O+54]), "+f"(d[O+55]), "+f"(d[O+56]), "+f"(d[O+57]), "+f"(d[O+58]), "+f"(d[O+59]), "+f"(d[O+60]), "+f"(d[O+61]), "+f"(d[O+62]), "+f"(d[O+63])
   : "l"(da), "l"(db), "n"(TB & 1), "n"(TB >> 1), "r"(sd));
}
template<int O,int TB,int ACC,int NN> __device__ __forceinline__ void mma_rs128(float (&d)[NN], uint32_t a0, uint32_t a1, uint32_t a2, uint32_t a3, uint64_t db, int sd = 0){
  if constexpr (ACC == 1) asm volatile("wgmma.mma_async.sync.aligned.m64n128k16.f32.bf16.bf16 {%0,%1,%2,%3,%4,%5,%6,%7,%8,%9,%10,%11,%12,%13,%14,%15,%16,%17,%18,%19,%20,%21,%22,%23,%24,%25,%26,%27,%28,%29,%30,%31,%32,%33,%34,%35,%36,%37,%38,%39,%40,%41,%42,%43,%44,%45,%46,%47,%48,%49,%50,%51,%52,%53,%54,%55,%56,%57,%58,%59,%60,%61,%62,%63}, {%64,%65,%66,%67}, %68, 1, 1, 1, %69;"
   : "+f"(d[O+0]), "+f"(d[O+1]), "+f"(d[O+2]), "+f"(d[O+3]), "+f"(d[O+4]), "+f"(d[O+5]), "+f"(d[O+6]), "+f"(d[O+7]), "+f"(d[O+8]), "+f"(d[O+9]), "+f"(d[O+10]), "+f"(d[O+11]), "+f"(d[O+12]), "+f"(d[O+13]), "+f"(d[O+14]), "+f"(d[O+15]), "+f"(d[O+16]), "+f"(d[O+17]), "+f"(d[O+18]), "+f"(d[O+19]), "+f"(d[O+20]), "+f"(d[O+21]), "+f"(d[O+22]), "+f"(d[O+23]), "+f"(d[O+24]), "+f"(d[O+25]), "+f"(d[O+26]), "+f"(d[O+27]), "+f"(d[O+28]), "+f"(d[O+29]), "+f"(d[O+30]), "+f"(d[O+31]), "+f"(d[O+32]), "+f"(d[O+33]), "+f"(d[O+34]), "+f"(d[O+35]), "+f"(d[O+36]), "+f"(d[O+37]), "+f"(d[O+38]), "+f"(d[O+39]), "+f"(d[O+40]), "+f"(d[O+41]), "+f"(d[O+42]), "+f"(d[O+43]), "+f"(d[O+44]), "+f"(d[O+45]), "+f"(d[O+46]), "+f"(d[O+47]), "+f"(d[O+48]), "+f"(d[O+49]), "+f"(d[O+50]), "+f"(d[O+51]), "+f"(d[O+52]), "+f"(d[O+53]), "+f"(d[O+54]), "+f"(d[O+55]), "+f"(d[O+56]), "+f"(d[O+57]), "+f"(d[O+58]), "+f"(d[O+59]), "+f"(d[O+60]), "+f"(d[O+61]), "+f"(d[O+62]), "+f"(d[O+63])
   : "r"(a0), "r"(a1), "r"(a2), "r"(a3), "l"(db), "n"(TB));
  else if constexpr (ACC == 0) asm volatile("wgmma.mma_async.sync.aligned.m64n128k16.f32.bf16.bf16 {%0,%1,%2,%3,%4,%5,%6,%7,%8,%9,%10,%11,%12,%13,%14,%15,%16,%17,%18,%19,%20,%21,%22,%23,%24,%25,%26,%27,%28,%29,%30,%31,%32,%33,%34,%35,%36,%37,%38,%39,%40,%41,%42,%43,%44,%45,%46,%47,%48,%49,%50,%51,%52,%53,%54,%55,%56,%57,%58,%59,%60,%61,%62,%63}, {%64,%65,%66,%67}, %68, 0, 1, 1, %69;"
   : "=f"(d[O+0]), "=f"(d[O+1]), "=f"(d[O+2]), "=f"(d[O+3]), "=f"(d[O+4]), "=f"(d[O+5]), "=f"(d[O+6]), "=f"(d[O+7]), "=f"(d[O+8]), "=f"(d[O+9]), "=f"(d[O+10]), "=f"(d[O+11]), "=f"(d[O+12]), "=f"(d[O+13]), "=f"(d[O+14]), "=f"(d[O+15]), "=f"(d[O+16]), "=f"(d[O+17]), "=f"(d[O+18]), "=f"(d[O+19]), "=f"(d[O+20]), "=f"(d[O+21]), "=f"(d[O+22]), "=f"(d[O+23]), "=f"(d[O+24]), "=f"(d[O+25]), "=f"(d[O+26]), "=f"(d[O+27]), "=f"(d[O+28]), "=f"(d[O+29]), "=f"(d[O+30]), "=f"(d[O+31]), "=f"(d[O+32]), "=f"(d[O+33]), "=f"(d[O+34]), "=f"(d[O+35]), "=f"(d[O+36]), "=f"(d[O+37]), "=f"(d[O+38]), "=f"(d[O+39]), "=f"(d[O+40]), "=f"(d[O+41]), "=f"(d[O+42]), "=f"(d[O+43]), "=f"(d[O+44]), "=f"(d[O+45]), "=f"(d[O+46]), "=f"(d[O+47]), "=f"(d[O+48]), "=f"(d[O+49]), "=f"(d[O+50]), "=f"(d[O+51]), "=f"(d[O+52]), "=f"(d[O+53]), "=f"(d[O+54]), "=f"(d[O+55]), "=f"(d[O+56]), "=f"(d[O+57]), "=f"(d[O+58]), "=f"(d[O+59]), "=f"(d[O+60]), "=f"(d[O+61]), "=f"(d[O+62]), "=f"(d[O+63])
   : "r"(a0), "r"(a1), "r"(a2), "r"(a3), "l"(db), "n"(TB));
  else asm volatile("{\n.reg .pred p;\nsetp.ne.b32 p, %70, 0;\nwgmma.mma_async.sync.aligned.m64n128k16.f32.bf16.bf16 {%0,%1,%2,%3,%4,%5,%6,%7,%8,%9,%10,%11,%12,%13,%14,%15,%16,%17,%18,%19,%20,%21,%22,%23,%24,%25,%26,%27,%28,%29,%30,%31,%32,%33,%34,%35,%36,%37,%38,%39,%40,%41,%42,%43,%44,%45,%46,%47,%48,%49,%50,%51,%52,%53,%54,%55,%56,%57,%58,%59,%60,%61,%62,%63}, {%64,%65,%66,%67}, %68, p, 1, 1, %69;\n}"
   : "+f"(d[O+0]), "+f"(d[O+1]), "+f"(d[O+2]), "+f"(d[O+3]), "+f"(d[O+4]), "+f"(d[O+5]), "+f"(d[O+6]), "+f"(d[O+7]), "+f"(d[O+8]), "+f"(d[O+9]), "+f"(d[O+10]), "+f"(d[O+11]), "+f"(d[O+12]), "+f"(d[O+13]), "+f"(d[O+14]), "+f"(d[O+15]), "+f"(d[O+16]), "+f"(d[O+17]), "+f"(d[O+18]), "+f"(d[O+19]), "+f"(d[O+20]), "+f"(d[O+21]), "+f"(d[O+22]), "+f"(d[O+23]), "+f"(d[O+24]), "+f"(d[O+25]), "+f"(d[O+26]), "+f"(d[O+27]), "+f"(d[O+28]), "+f"(d[O+29]), "+f"(d[O+30]), "+f"(d[O+31]), "+f"(d[O+32]), "+f"(d[O+33]), "+f"(d[O+34]), "+f"(d[O+35]), "+f"(d[O+36]), "+f"(d[O+37]), "+f"(d[O+38]), "+f"(d[O+39]), "+f"(d[O+40]), "+f"(d[O+41]), "+f"(d[O+42]), "+f"(d[O+43]), "+f"(d[O+44]), "+f"(d[O+45]), "+f"(d[O+46]), "+f"(d[O+47]), "+f"(d[O+48]), "+f"(d[O+49]), "+f"(d[O+50]), "+f"(d[O+51]), "+f"(d[O+52]), "+f"(d[O+53]), "+f"(d[O+54]), "+f"(d[O+55]), "+f"(d[O+56]), "+f"(d[O+57]), "+f"(d[O+58]), "+f"(d[O+59]), "+f"(d[O+60]), "+f"(d[O+61]), "+f"(d[O+62]), "+f"(d[O+63])
   : "r"(a0), "r"(a1), "r"(a2), "r"(a3), "l"(db), "n"(TB), "r"(sd));
}

#define NEARLY 0
#define XAHEAD 3
#define HEADN 6
#define WBATCH 1
#define WB 8
#define WSLEEP 20
#define XSPREAD 4
#define NOSEND 0
#define MSPLIT 2
#define PFALL 1
#define L2PF 0
#define STAG 0
#define EPF 2
#define XNB 2
#define FNB 0
#define GNB 0
#define TH 4
#define PF0 4
#define FSPLIT 1
#define MGLU 1
#define SPC 2
#define TL 14
#define GKB 4
#define T0A 8
#define TGATE 1
#define FIN32 1
#define SPACE 100
#define WPF 1
#define WAFTER 7
#define WPACE 0
#define GATE_AT 4
#define TPACE 40
#define PFMODE 0
#define MAPMODE 1
template <int V> struct IC { static constexpr int value = V; };
struct Maps { CUtensorMap x, ft, g64, u64, e, wr, wi, xs, ts, t, g32, u32, d224; };

constexpr int NCTA = 130;
constexpr int U = 16384;
constexpr int TB = 36864;
constexpr int OFF_RING = 8 * U, OFF_Z = 12 * U, OFF_XB = 12 * U, OFF_T = 13 * U, OFF_D = OFF_T;
constexpr int OFF_BAR = 14 * U, OFF_SP = OFF_BAR + 512, OFF_G = OFF_SP + 1024 + 128;
constexpr int SMEM_BYTES = OFF_G + 512;
constexpr int B_FX = 0, B_FA = 8, B_FT = 12, B_Z = 16, B_W = 24, B_HX = 25, B_TL = 26, B_HP = 27, B_WR = 30, B_E0 = 34;
constexpr int B_EA = 35, B_ET = 39, B_PZ = 43, B_RDY = 45, B_FE = 46;
constexpr int B_T = 50, B_XS = 51, B_G = 53, B_RD0 = 54, NBAR = 55;
__host__ __device__ constexpr int rslot(int n) { return n & 3; }
__host__ __device__ constexpr int rpar(int n) { return (n >> 2) & 1; }

__global__ void __cluster_dims__(2, 1, 1) __launch_bounds__(512, 1)
fused_kernel(Work* __restrict__ ws, const uint16_t* __restrict__ dtab, const __nv_bfloat16* __restrict__ w_r, const __nv_bfloat16* __restrict__ w_i,
             const __nv_bfloat16* __restrict__ gate_w, const __nv_bfloat16* __restrict__ x, __nv_bfloat16* __restrict__ out,
             const __grid_constant__ Maps maps) {
  extern __shared__ __align__(1024) uint8_t smem[];
  const uint32_t sb = smem_u32(smem);
  const uint32_t bars = sb + OFF_BAR;
  const int tid = threadIdx.x, lane = tid & 31;
  const bool helper = blockIdx.x >= 128;
  const int cl = (blockIdx.x >> 1) & 63, rank = blockIdx.x & 1;
  const int q4 = (cl & 1) | ((cl >> 2) & 2), rb = ((cl >> 1) & 3) | ((cl >> 4) << 2);
  const int j = 2 * q4 + rank;
  const int f_full = 448 * q4 + (rank ? 256 : 0);
  const int f_half = 448 * q4 + (rank ? 224 : 192);
  const int kg = 2 * j + (rb >> 3), tn = rb & 7;

  if (tid == 64) { PROF_EV(0); PROF_CK(40); }
  if (tid < 64 && elect_one()) {
    if (tid < 32) {
      mbar_init(bars + 8 * B_FX, 1); mbar_init(bars + 8 * (B_FX + 1), 1);
      asm volatile("fence.mbarrier_init.release.cluster;" ::: "memory");
      if (!helper) {
#pragma unroll
        for (int q = 0; q < 2; q++) {
          tma3d(sb + q * U, &maps.x, bars + 8 * (B_FX + q), 64 * q, 0, 2 * rb);
          tma2d(sb + OFF_XB + q * 8192, &maps.ft, bars + 8 * (B_FX + q), 64 * q, 64 * j);
          mbar_expect_tx(bars + 8 * (B_FX + q), U + 8192);
        }
        PROF_EV(33);
      }
    } else {
#pragma unroll
      for (int i = 1; i < 4; i++) asm volatile("prefetch.tensormap [%0];" ::"l"((const char*)&maps + i * 128) : "memory");
    }
  }
  const int warp = __shfl_sync(0xffffffffu, tid >> 5, 0);
  if (warp < 8) {
    if (!helper && warp == 2) {
      const int r = 16 * j + (tid & 15);
      asm volatile("prefetch.global.L2 [%0];" ::"l"(x + (size_t)(2 * rb + (r >> 6) + 32 * (r & 63)) * 512 + 64 * (lane >> 4)));
    }
    asm volatile("barrier.cluster.arrive.relaxed.aligned;" ::: "memory");
    asm volatile("setmaxnreg.inc.sync.aligned.u32 192;");
    if (!helper) {
      const int wg = warp >> 2, w = warp & 3, g = lane >> 2;
      const bool elect = (tid & 127) == 0;
      float cX[32], cA[64], cB[64], cC[64], ci[64], ct[64];
      const int zero = blockIdx.x >> 16;
      uint32_t h[56], yf[16];
      const uint32_t d0 = (sb & 0x3FFFF) >> 4;
      const uint32_t dK = d0 | (1u << 16), dN = d0 | (512u << 16);
      const uint32_t dX = dK + wg * 512;
      constexpr uint32_t RING = OFF_RING >> 4;
      auto waitA = [&](int n) { mbar_wait(bars + 8 * (B_FA + rslot(n)), rpar(n)); };
      auto freeA = [&](int n) { mbar_arrive_if(elect, bars + 8 * (B_EA + rslot(n))); };
      auto nop = [] {};

      asm volatile("bar.sync 0, 384;" ::: "memory");
#pragma unroll 1
      for (int i = 0; i < 4; i++) {
        const uint64_t dx = d128(dX + i * 2048), df = d128(dK + (OFF_XB >> 4) + (i & 1) * 1024);
        mbar_wait(bars + 8 * (B_FX + 2 * i), 0);
        wg_fence();
        mma_ss64<0, 0, 2>(cX, df, dx, i);
        mma_ss64<0, 0, 1>(cX, df + 2, dx + 2);
        wg_commit(); wg_wait<1>();
        mbar_arrive_if(elect && i, bars + 8 * (B_EA + rslot(i - 1)));
        mma_ss64<0, 0, 1>(cX, df + 4, dx + 4);
        mma_ss64<0, 0, 1>(cX, df + 6, dx + 6);
        if (i == 0 && tid == 0) PROF_EV(1);
        mbar_wait(bars + 8 * (B_FX + 2 * i + 1), 0);
        wg_fence();
#pragma unroll
        for (int k = 0; k < 4; k++) mma_ss64<0, 0, 1>(cX, df + (512 + k * 2), dx + (1024 + k * 2));
        wg_commit();
        waitA(i);
        wg_fence();
        const uint64_t da = d128(dX + i * 1024), db = d128(dN + RING + i * 1024);
        mma_ss128<0, 1, 2>(cA, da, db, i);
        wg_commit(); wg_wait<1>();
        mbar_arrive_if(elect, bars + 8 * (B_FE + i));
#pragma unroll
        for (int k = 1; k < 4; k++) mma_ss128<0, 1, 1>(cA, da + k * 2, db + k * 128);
        wg_commit();
      }
      fence_regs<0, 32>(cX);
#pragma unroll
      for (int e = 0; e < 16; e++) yf[e] = pack_pin(cX[2 * e], cX[2 * e + 1]);
      if (tid == 0) { PROF_EV(2); PROF_CK(42); }
      {
        waitA(4); mbar_wait(bars + 8 * B_E0, 0);
        const uint64_t de = d128(dN + (wg ? RING : OFF_XB >> 4));
        wg_fence();
        mma_rs128<0, 1, 0>(cB, yf[0], yf[1], yf[2], yf[3], de);
        wg_commit();
        wg_wait<1>();
        freeA(3);
#pragma unroll
        for (int k = 1; k < 4; k++) mma_rs128<0, 1, 1>(cB, yf[4 * k], yf[4 * k + 1], yf[4 * k + 2], yf[4 * k + 3], de + k * 128);
        wg_commit();
      }
      bool rel = false;
      auto acquire = [&](int n) {
        rel = elect;
        if (!mbar_try(bars + 8 * (B_FA + rslot(n)), rpar(n))) { wg_wait<0>(); freeA(n - 1); rel = false; waitA(n); }
      };
      auto freeP = [&](int n) { mbar_arrive_if(rel, bars + 8 * (B_EA + rslot(n - 1))); };
      auto ffn_step = [&](auto first, auto split, float (&acc)[64], int n, int kb, auto done, auto work) {
        constexpr int SPLIT = decltype(split)::value;
        acquire(n);
        wg_fence();
        const uint64_t dx = d128(dX + kb * 1024), db = d128(dN + RING + rslot(n) * 1024);
        mma_ss128<0, 1, decltype(first)::value>(acc, dx, db, kb);
#pragma unroll
        for (int k = 1; k < SPLIT; k++) mma_ss128<0, 1, 1>(acc, dx + k * 2, db + k * 128);
        wg_commit();
        work();
        wg_wait<1>();
        freeP(n);
        done();
        if (SPLIT < 4) {
          wg_fence();
#pragma unroll
          for (int k = SPLIT; k < 4; k++) mma_ss128<0, 1, 1>(acc, dx + k * 2, db + k * 128);
          wg_commit();
        }
      };
      {
        const int s0 = 2 * rb + wg, kr = 2 * ((s0 & 1) | ((s0 & 4) >> 1));
        const int m = lane >> 3, r = lane & 7;
        const uint32_t a0 = sb + OFF_XB + wg * 8192 + (((w >> 1) * 8 + (m >> 1)) * 2 + (w & 1)) * 256 + (m & 1) * 128 + ((r ^ (kr + (m & 1))) << 4);
        ffn_step(IC<1>(), IC<4>(), cA, 5, 4, [&] { fence_regs<0, 64>(cB); }, nop);
        asm volatile("bar.sync 5, 256;" ::: "memory");
        auto stage = [&](int i) {
          stsm4t(a0 + i * 1024, pack_bf16(cB[8 * i] - cB[34 + 8 * i], cB[8 * i + 1] - cB[35 + 8 * i]),
                 pack_bf16(cB[32 + 8 * i] + cB[8 * i + 2], cB[33 + 8 * i] + cB[8 * i + 3]),
                 pack_bf16(cB[8 * i + 4] - cB[38 + 8 * i], cB[8 * i + 5] - cB[39 + 8 * i]),
                 pack_bf16(cB[36 + 8 * i] + cB[8 * i + 6], cB[37 + 8 * i] + cB[8 * i + 7]));
          if (j == 0 && w == 0) {
            const uint32_t a1 = r ? sb + OFF_SP + 1024 : sb + OFF_SP + wg * 512 + (m & 1) * 256 + (m >> 1) * 128;
#pragma unroll
            for (int n = 2 * i; n < 2 * i + 2; n++)
              asm volatile("stmatrix.sync.aligned.m8n8.x4.shared.b16 [%0], {%1,%2,%3,%4};" ::"r"(a1 + ((n ^ (kr + (m >> 1)) ^ r) << 4)),
                           "r"(pack_bf16(cB[4 * n], cB[4 * n + 1])), "r"(pack_bf16(cB[4 * n + 2], cB[4 * n + 3])),
                           "r"(pack_bf16(cB[32 + 4 * n], cB[33 + 4 * n])), "r"(pack_bf16(cB[34 + 4 * n], cB[35 + 4 * n])) : "memory");
          }
        };
        auto publish = [&] {
          asm volatile("fence.proxy.async.shared::cta;" ::: "memory");
          __syncwarp();
          mbar_arrive_if(lane == 0, bars + 8 * (B_XS + wg));
          if (tid == 0) PROF_EV(3);
        };
        stage(0);
        ffn_step(IC<1>(), IC<FSPLIT>(), cA, 6, 5, nop, nop);
        stage(1);
        ffn_step(IC<1>(), IC<FSPLIT>(), cA, 7, 6, nop, nop);
        stage(2);
        ffn_step(IC<1>(), IC<2>(), cA, 8, 7, [&] { stage(3); }, nop);
        publish();
      }
      uint32_t gb0 = 0, gb1 = 0;
      uint32_t ob[2] = {0, 0};
      auto glu = [&](auto& acc, int half, int ho, int i0, int i1) {
#pragma unroll
        for (int i = i0; i < i1; i++)
          asm volatile("{\n.reg .b32 a, b;\ncvt.rn.relu.bf16x2.f32 a, %2, %1;\ncvt.rn.bf16x2.f32 b, %4, %3;\nmul.rn.bf16x2 a, a, b;\nmul.rn.bf16x2 %0, a, %5;\n}"
                       : "=r"(h[ho + i]) : "f"(acc[2 * i]), "f"(acc[2 * i + 1]), "f"(acc[half + 2 * i]), "f"(acc[half + 1 + 2 * i]), "r"(ob[i & 1]) : "memory");
      };
      ffn_step(IC<2>(), IC<1>(), cB, 9, zero, nop, nop);
#pragma unroll 1
      for (int kb = 1; kb < 8; kb++)
        ffn_step(IC<1>(), IC<FSPLIT>(), cB, 9 + kb, kb, nop, [&] {
          if (kb == GKB) {
            mbar_wait(bars + 8 * B_G, 0);
            asm volatile("ld.shared.u32 %0, [%2];\nld.shared.u32 %1, [%2+32];" : "=r"(gb0), "=r"(gb1) : "r"(sb + OFF_G + (wg * 64 + w * 16 + g) * 4) : "memory");
          } else if (kb == 5 + 2 * wg) {
            ob[0] = pack_bf16(1.0f - bf_hi(gb0), 1.0f - bf_hi(gb0)); ob[1] = pack_bf16(1.0f - bf_hi(gb1), 1.0f - bf_hi(gb1));
            glu(cA, 32, 0, 0, 16);
          }
        });
      const uint32_t tag = gb0 & 1;
      const float g0 = bf_hi(gb0), g1 = bf_hi(gb1);
      if (tid == 0) { PROF_EV(4); PROF_CK(43); }
      auto m_step = [&](auto first, int i) {
        acquire(17 + i);
        wg_fence();
        const uint64_t dx = d128(dX + i * 2048), dm = d64(dN + RING + rslot(17 + i) * 1024);
        mma_ss64<0, 1, decltype(first)::value>(ct, dx, dm);
#pragma unroll
        for (int k = 1; k < MSPLIT; k++) mma_ss64<0, 1, 1>(ct, dx + ((k >> 2) * 1024 + (k & 3) * 2), dm + k * 64);
        wg_commit();
        wg_wait<1>();
        freeP(17 + i);
        wg_fence();
#pragma unroll
        for (int k = MSPLIT; k < 8; k++) mma_ss64<0, 1, 1>(ct, dx + ((k >> 2) * 1024 + (k & 3) * 2), dm + k * 64);
        wg_commit();
      };
      m_step(IC<0>(), 0);
#pragma unroll 1
      for (int i = 1; i < 5; i++) {
        if (i == 1 + 2 * wg) glu(cB, 32, 16, 0, 16);
        if (i < 4) m_step(IC<1>(), i);
      }
      if (tid == 0) { PROF_EV(5); PROF_CK(44); }
      ffn_step(IC<0>(), IC<1>(), cC, 21, 0, nop, nop);
#pragma unroll 1
      for (int kb = 1; kb < 8; kb++)
        ffn_step(IC<1>(), IC<FSPLIT>(), cC, 21 + kb, kb, [&] { mbar_arrive_if(elect && !(kb & 1), bars + 8 * (B_ET + (kb >> 1) - 1)); }, [&] {
          if (kb == 1 + wg) glu(ct, 16, 48, 0, 8);
        });

      auto twait = [&](uint32_t bar, uint32_t par, int) { mbar_wait(bar, par); };
      const int fo = warp * 128 + lane;
      auto fetch = [&](uint4 (&pv)[4], int z) {
        twait(bars + 8 * (z < 4 ? B_Z + 2 * z + wg : B_HP + z - 4), 0, 8 + z);
        const uint8_t* src = smem + (z < 4 ? OFF_Z - z * U : z == 4 ? OFF_T : (z - 5) * U) + fo * 16;
#pragma unroll
        for (int i = 0; i < 4; i++) pv[i] = *(const uint4*)(src + i * 512);
      };
      auto check = [&](uint4 (&pv)[4], int z) {
#pragma unroll 1
        for (int n = 0; __any_sync(0xffffffffu, ((pv[0].x ^ tag) | (pv[1].x ^ tag) | (pv[2].x ^ tag) | (pv[3].x ^ tag)) & 1); n++) {
#pragma unroll
          for (int i = 0; i < 4; i++) pv[i] = ld_x4(ws->part + (size_t)((rb * 8 + j) * 3 + z - 4) * 1024 + fo + i * 32);
          if (n > (1 << 21)) __trap();
        }
#pragma unroll
        for (int i = 0; i < 4; i++) pv[i].x &= ~1u;
      };
      const uint32_t peerZ = mapa(sb + OFF_Z + fo * 16, rank ^ 1), peerB = mapa(bars + 8 * (B_Z + wg), rank ^ 1);
      auto tile_mma = [&](auto off, int t, int k0, int k1, int init) {
        constexpr int O = decltype(off)::value;
        const uint64_t db = d128(dN + (t & 3) * (TB >> 4)), dw = db + rank * 256, dm = db + (rank ? 0 : 1536);
#pragma unroll
        for (int k = k0; k < k1; k++) {
          if (k == 0) mma_rs64<O, 1, 2>(ct, h[0], h[1], h[2], h[3], dw, init);
          else if (k < 14) mma_rs64<O, 1, 1>(ct, h[4 * k], h[4 * k + 1], h[4 * k + 2], h[4 * k + 3], k < 12 ? dw + k * 128 : dm + (k - 12) * 128);
          else mma_rs64<O, 1, 1>(ct, yf[4 * k - 56], yf[4 * k - 55], yf[4 * k - 54], yf[4 * k - 53], db + k * 128);
        }
      };
      uint4 pv[4] = {};
      auto tile = [&](auto off, int t) {
        constexpr int P = 32 - decltype(off)::value;
        const bool grid = t >= 4 && t < 7, pre = t >= 3 && t != 6;
        const int zo = grid ? t - 4 : t == 7 ? 3 : t - 1, z = t - 3;
        const int owner = rb * 8 + 2 * ((q4 + zo + 1) & 3) + rank;
        uint4* dst = ws->part + (size_t)(owner * 3 + zo) * 1024 + fo;
        const uint32_t src = sb + (z < 4 ? OFF_Z - z * U : OFF_T) + fo * 16;
        twait(bars + 8 * (B_FT + (t & 3)), t >> 2, t);
        wg_fence();
        tile_mma(off, t, 0, TH, zero);
        wg_commit();
        wg_wait<1>();
        mbar_arrive_if(elect && t < 6, bars + 8 * (B_ET + t - 1));
        if (t < 3) twait(bars + 8 * (t == 1 ? B_RD0 : B_RDY), 0, 14 + t);
        fence_regs<P, 32>(ct);
#pragma unroll
        for (int i = 0; i < 4; i++) {
          pv[i].x = (add_bf2(pv[i].x, pack_bf16(ct[P + 8 * i], ct[P + 8 * i + 1])) & ~(uint32_t)grid) | (tag & grid);
          pv[i].y = add_bf2(pv[i].y, pack_bf16(ct[P + 8 * i + 2], ct[P + 8 * i + 3]));
          pv[i].z = add_bf2(pv[i].z, pack_bf16(ct[P + 8 * i + 4], ct[P + 8 * i + 5]));
          pv[i].w = add_bf2(pv[i].w, pack_bf16(ct[P + 8 * i + 6], ct[P + 8 * i + 7]));
        }
        if (grid) {
#pragma unroll
          for (int i = 0; i < 4; i++)
            asm volatile("st.relaxed.gpu.global.v4.u32 [%0], {%1,%2,%3,%4};" ::"l"(dst + i * 32), "r"(pv[i].x), "r"(pv[i].y), "r"(pv[i].z), "r"(pv[i].w) : "memory");
          hint_add_if(lane == 0, &ws->cntP[32 * owner + 8 * zo]);
        }
        auto share = [&](int i) {
          asm volatile("st.async.weak.shared::cluster.mbarrier::complete_tx::bytes.v4.b32 [%0], {%2,%3,%4,%5}, [%1];" ::"r"(peerZ - zo * U + i * 512),
                       "r"(peerB + 16 * zo), "r"(pv[i].x), "r"(pv[i].y), "r"(pv[i].z), "r"(pv[i].w) : "memory");
        };
        if (P == 0 && t == 7) { share(1); share(2); share(3); }
#pragma unroll
        for (int i = 0; i < 4; i++) {
          if (i == 0 ? !grid : t < 4) share(i);
          wg_fence();
          tile_mma(off, t, TH + SPC * i, i < 3 ? TH + SPC * i + SPC : TL, 0);
        }
        wg_commit();
        if (pre) twait(bars + 8 * (z < 4 ? B_Z + 2 * z + wg : B_HP), 0, 8 + z);
        wg_fence();
#pragma unroll
        for (int i = 0; i < 4; i++) {
          asm volatile("{\n.reg .pred p;\nsetp.ne.b32 p, %5, 0;\nmov.b32 %0, 0;\nmov.b32 %1, 0;\nmov.b32 %2, 0;\nmov.b32 %3, 0;\n@p ld.shared.v4.u32 {%0,%1,%2,%3}, [%4];\n}"
                       : "=r"(pv[i].x), "=r"(pv[i].y), "=r"(pv[i].z), "=r"(pv[i].w) : "r"(src + i * 512), "r"((int)pre) : "memory");
          tile_mma(off, t, TL + i, i < 3 ? TL + 1 + i : 18, 0);
        }
        wg_commit();
      };
      asm volatile("barrier.cluster.wait.aligned;" ::: "memory");
      twait(bars + 8 * B_FT, 0, 0);
      wg_fence();
      tile_mma(IC<0>(), 0, 0, T0A, zero);
      wg_commit();
      waitA(29 + wg);
      wg_wait<1>();
      mbar_arrive_if(elect, bars + 8 * (B_ET + 3));
      glu(cC, 32, 32, 0, 16);
      if (tid == 0) PROF_EV(6);
      if (tid == 128) PROF_EV(27);
      mbar_wait(bars + 8 * (j == 0 ? B_T : B_TL), 0);
      if (tid == 0) { PROF_EV(7); PROF_CK(45); }
      wg_fence();
      {
        const uint64_t dt = d128(dN + (OFF_T >> 4) + wg * 512), de = d128(dK + RING + (1 + wg) * 1024);
        mma_ss64<0, 1, 0>(ci, de, dt);
        mma_ss64<32, 1, 0>(ci, de + 512, dt);
#pragma unroll
        for (int k = 1; k < 4; k++) {
          mma_ss64<0, 1, 1>(ci, de + k * 2, dt + k * 128);
          mma_ss64<32, 1, 1>(ci, de + (512 + k * 2), dt + k * 128);
        }
        wg_commit();
      }
      tile_mma(IC<0>(), 0, T0A, 14, 0);
      wg_commit();
      wg_wait<1>();
      if (elect) asm volatile("mbarrier.arrive.shared::cluster.b64 _, [%0];" ::"r"(mapa(bars + 8 * B_RDY, rank ^ 1)) : "memory");
      mbar_arrive_if(elect, bars + 8 * (B_PZ + 1));
      fence_regs<0, 64>(ci);
#pragma unroll
      for (int i = 0; i < 16; i++) {
        const float gg = ((i & 1) ? g1 : g0) * (2.0f / (2048.0f * 512.0f));
        if (i & 2) yf[i] = pack_pin((ci[2 * i] - ci[28 + 2 * i]) * gg, (ci[2 * i + 1] - ci[29 + 2 * i]) * gg);
        else yf[i] = pack_pin((ci[2 * i] + ci[36 + 2 * i]) * gg, (ci[2 * i + 1] + ci[37 + 2 * i]) * gg);
      }
      wg_fence();
      tile_mma(IC<0>(), 0, 14, 18, 0);
      wg_commit();
      if (tid == 0) PROF_EV(8);
      if (tid == 128) PROF_EV(28);
#pragma unroll 1
      for (int t = 1;; t += 2) {
        tile(IC<32>(), t);
        if (t == 7) break;
        tile(IC<0>(), t + 1);
      }
      if (tid == 0) { PROF_EV(9); PROF_CK(46); }
      if (tid == 128) PROF_EV(29);
      {
        uint4 p1[4], p2[4];
        auto acc4 = [&](uint4 (&d)[4], const uint4 (&a)[4]) {
#pragma unroll
          for (int i = 0; i < 4; i++) { d[i].x = add_bf2(d[i].x, a[i].x); d[i].y = add_bf2(d[i].y, a[i].y); d[i].z = add_bf2(d[i].z, a[i].z); d[i].w = add_bf2(d[i].w, a[i].w); }
        };
        uint4 p3[4];
        fetch(p1, 5);
        fetch(p2, 3);
        if (tid == 0) PROF_EV(25);
        wg_wait<0>();
        fence_regs<32, 32>(ct);
        fetch(p3, 6);
        if (tid == 0) PROF_EV(24);
        check(pv, 4); check(p1, 5); check(p3, 6);
        acc4(pv, p1); acc4(p2, p3);
#pragma unroll
        for (int i = 0; i < 4; i++) {
          pv[i].x = pack_bf16(ct[32 + 8 * i] + bf_lo(pv[i].x) + bf_lo(p2[i].x), ct[33 + 8 * i] + bf_hi(pv[i].x) + bf_hi(p2[i].x));
          pv[i].y = pack_bf16(ct[34 + 8 * i] + bf_lo(pv[i].y) + bf_lo(p2[i].y), ct[35 + 8 * i] + bf_hi(pv[i].y) + bf_hi(p2[i].y));
          pv[i].z = pack_bf16(ct[36 + 8 * i] + bf_lo(pv[i].z) + bf_lo(p2[i].z), ct[37 + 8 * i] + bf_hi(pv[i].z) + bf_hi(p2[i].z));
          pv[i].w = pack_bf16(ct[38 + 8 * i] + bf_lo(pv[i].w) + bf_lo(p2[i].w), ct[39 + 8 * i] + bf_hi(pv[i].w) + bf_hi(p2[i].w));
        }
        if (tid == 0) PROF_EV(14);
        const uint32_t stg = sb + OFF_T + warp * 2048;
        const int mr = (lane & 7) + ((lane >> 3) & 1) * 8, mc = lane >> 4;
#pragma unroll
        for (int i = 0; i < 4; i++)
          asm volatile("stmatrix.sync.aligned.m8n8.x4.shared.b16 [%0], {%1,%2,%3,%4};" ::"r"(stg + mr * 128 + (((2 * i + mc) ^ (mr & 7)) << 4)), "r"(pv[i].x),
                       "r"(pv[i].y), "r"(pv[i].z), "r"(pv[i].w) : "memory");
        __syncwarp();
#pragma unroll
        for (int i = 0; i < 4; i++) {
          const int r = 4 * i + (lane >> 3), c = lane & 7;
          const uint4 v = *(const uint4*)(smem + OFF_T + warp * 2048 + r * 128 + ((c ^ (r & 7)) << 4));
          *(uint4*)(out + (size_t)(2 * rb + wg + 32 * (16 * w + r)) * 512 + 64 * j + 8 * c) = v;
        }
      }
      if (tid == 0) { PROF_EV(15); PROF_CK(41); }
      if (tid == 128) PROF_EV(30);
    }
  } else if (warp < 12) {
    asm volatile("setmaxnreg.dec.sync.aligned.u32 104;");
    asm volatile("barrier.cluster.arrive.relaxed.aligned;" ::: "memory");
    const int t = tid - 256, w = warp - 8;
    const uint32_t ep = ld_x1(&ws->epoch[blockIdx.x * 8]);
    const uint32_t tag = (ep + 1) & 1;
    auto w_issue = [&](const CUtensorMap* m) {

      if (elect_one()) { mbar_expect_tx(bars + 8 * (B_WR + w), 3072); tma4d(sb + OFF_T + w * 3072, m, bars + 8 * (B_WR + w), 16 * kg, 0, 2 * w, tn); }

          __syncwarp();
    };
    auto gate_rows = [&] {
      const int r = 16 * j + 4 * w + (lane >> 3);
      const uint4* pg = (const uint4*)gate_w + (lane & 7);
      {
        float a = 0.f;
        asm volatile("bar.sync 4, 256;" ::: "memory");
#pragma unroll 1
        for (int hf = 0; hf < 2; hf++) {
          uint4 v[4], u[4];
#pragma unroll
          for (int kb = 0; kb < 4; kb++) v[kb] = __ldg(pg + (4 * hf + kb) * 8);
          mbar_wait(bars + 8 * (B_FE + 1 + 2 * hf), 0);
          if (hf) w_issue(&maps.wr);
#pragma unroll
          for (int kb = 0; kb < 4; kb++) u[kb] = *(const uint4*)(smem + (4 * hf + kb) * U + r * 128 + (((lane ^ r) & 7) << 4));
#pragma unroll
          for (int kb = 0; kb < 4; kb++) {
            const uint32_t uu[4] = {u[kb].x, u[kb].y, u[kb].z, u[kb].w}, vv[4] = {v[kb].x, v[kb].y, v[kb].z, v[kb].w};
#pragma unroll
            for (int e = 0; e < 4; e++) {
              uint32_t pr;
              asm("mul.rn.bf16x2 %0, %1, %2;" : "=r"(pr) : "r"(uu[e]), "r"(vv[e]));
              a += bf_lo(pr) + bf_hi(pr);
            }
          }
        }
#pragma unroll
        for (int o = 4; o; o >>= 1) a += __shfl_xor_sync(0xffffffffu, a, o);
        if ((lane & 7) == 0)
          asm volatile("st.relaxed.gpu.global.u32 [%0], %1;" ::"l"(ws->gate + rb * 128 + r),
                       "r"(pack_bf16(0.f, __fdividef(1.0f, 1.0f + __expf(-bf_lo(pack_bf16(a, 0.f))))) | tag) : "memory");
        if (t == 0) PROF_EV(18);
      }
    };
    {
      const int g = lane >> 2, q = lane & 3;
      uint32_t wf[32];
      if (!helper) {
        gate_rows();
        const uint32_t wa = sb + OFF_T + w * (3072 + 4) + q * 48 + g * 2;
#pragma unroll 1
        for (int ri = 0; ri < 2; ri++) {
          mbar_wait(bars + 8 * (B_WR + w), ri);
#pragma unroll
          for (int n2 = 0; n2 < 32 / WB; n2++) {
            uint32_t v[WB];
#pragma unroll
            for (int i = 0; i < WB; i++) {
              const int e = n2 * WB + i;
              asm volatile("ld.shared.u16 %0, [%1];" : "=r"(v[i]) : "r"(wa + ((e >> 1) & 7) * 192 + (e & 1) * (1536 + 2) + (e >> 4) * 16) : "memory");
            }
#pragma unroll
            for (int i = 0; i < WB; i++) wf[n2 * WB + i] = __byte_perm(wf[n2 * WB + i], v[i], 0x5432);
            if (WSLEEP) { asm volatile("nanosleep.u32 %0;" ::"r"(WSLEEP + (v[WB - 1] >> 16)) : "memory"); }
          }
          __syncwarp();
          if (ri == 0) w_issue(&maps.wi);
        }
        asm volatile("bar.sync 1, 128;" ::: "memory");
        if (t == 0) PROF_EV(11);
      } else {
        asm volatile("bar.sync 4, 256;" ::: "memory");
        hint_wait(&ws->cntW[0], (ep + 1) * 128u);
        const uint32_t t0 = (uint32_t)clock();
#pragma unroll 1
        for (;;) {
          uint32_t bad = 0;
#pragma unroll
          for (int i = 0; i < 32; i++) {
            const float2 v = ld_x2((const float2*)ws->Wh + (i >> 4) * 2048 + 16 * w + g + 8 * (i & 1) + 64 * q + ((i >> 1) & 7) * 256);
            wf[i] = __float_as_uint(v.x); bad |= __float_as_uint(v.y) ^ tag;
          }
          if (!__any_sync(0xffffffffu, bad & 1)) break;
          spin_guard(t0);
        }
        if (t == 0) PROF_EV(11);
      }
      if (w == 0 && elect_one()) { mbar_expect_tx(bars + 8 * B_W, 8192); bulk_load(sb + OFF_D, dtab, 8192, bars + 8 * B_W); }
      asm volatile("barrier.cluster.wait.aligned;" ::: "memory");
      mbar_wait(bars + 8 * B_W, 0);
      mbar_wait(bars + 8 * B_HX, 0);
      if (t == 0) PROF_EV(12);
      const uint32_t dd = (sb & 0x3FFFF) >> 4;
      const uint64_t dF = d128((dd + (OFF_D >> 4)) | (512u << 16)), dI = d128((dd + (OFF_D >> 4)) | (1u << 16)), dA = d128((dd + (OFF_XB >> 4)) | (512u << 16));
      float az[32];
      const int zero = blockIdx.x >> 16;
      uint32_t pf[32];
#pragma unroll
      for (int mt = 0; mt < 2; mt++) {
        wg_fence();
        if (mt == 0) mma_ss64<0, 3, 0>(az, dA, dF);
        else mma_ss64<0, 3, 2>(az, dA + 512, dF, zero);
#pragma unroll
        for (int k = 1; k < 4; k++) mma_ss64<0, 3, 1>(az, dA + (mt * 512 + k * 128), dF + k * 128);
        wg_commit();
        wg_wait<0>();
        fence_regs<0, 32>(az);
#pragma unroll
        for (int i = 0; i < 16; i++) {
          const float wr = bf_lo(wf[16 * mt + i]), wi = bf_hi(wf[16 * mt + i]);
          pf[16 * mt + i] = pack_pin(fmaf(az[2 * i], wr, -az[2 * i + 1] * wi), fmaf(az[2 * i], wi, az[2 * i + 1] * wr));
        }
      }
      if (t == 0) PROF_EV(16);
      {
        const int m = lane >> 3, r = lane & 7;
        const int sl = 2 * (m >> 1) + ((r >> 1) & 1) + 4 * (r >> 2);
        const uint32_t a0 = sb + OFF_XB + (2 * w + (m & 1)) * 2048 + sl * 64;
        uint32_t pk[16];
#pragma unroll
        for (int mt = 0; mt < 3; mt++) {
          if (mt < 2) {
            wg_fence();
            mma_rs64<0, 0, 2>(az, pf[16 * mt], pf[16 * mt + 1], pf[16 * mt + 2], pf[16 * mt + 3], dI, mt ? (int)helper : zero);
#pragma unroll
            for (int k = 1; k < 4; k++) mma_rs64<0, 0, 1>(az, pf[16 * mt + 4 * k], pf[16 * mt + 4 * k + 1], pf[16 * mt + 4 * k + 2], pf[16 * mt + 4 * k + 3], dI + k * 2);
            wg_commit();
          }
          if (mt > 0 && !helper) {
#pragma unroll
            for (int i = 0; i < 4; i++) stsm4t(a0 + ((((mt - 1) * 2 + (r & 1)) ^ (sl >> 1)) << 4) + i * 512, pk[4 * i], pk[4 * i + 1], pk[4 * i + 2], pk[4 * i + 3]);
          }
          if (mt < 2) {
            wg_wait<0>();
            fence_regs<0, 32>(az);
#pragma unroll
            for (int i = 0; i < 16; i++) pk[i] = pack_pin(az[2 * i], az[2 * i + 1]);
          }
        }
      }
      if (helper) {
#pragma unroll
        for (int i = 0; i < 16; i++) {
          const int n = i >> 1, s0 = 8 * (n >> 1) + 2 * (n & 1) + (q & 1) + 4 * (q >> 1);
          if ((n & 1) == (int)(blockIdx.x & 1)) st_u2(ws->Ts + s0 * 64 + 16 * w + g + 8 * (i & 1), pack_bf16(az[2 * i], az[2 * i + 1]), tag);
        }
        __syncwarp();
        hint_add_if(lane == 0, &ws->cntH[0]);
        if (t == 0) { ws->epoch[blockIdx.x * 8] = ep + 1; PROF_EV(13); }
      } else {
        asm volatile("fence.proxy.async.shared::cta;" ::: "memory");
        __syncwarp();
        if (elect_one()) {
          if (t == 0) PROF_EV(17);
          if (SPACE) __nanosleep(SPACE * w);
          asm volatile("cp.async.bulk.tensor.3d.global.shared::cta.bulk_group [%0, {%2, %3, %4}], [%1];" ::"l"(&maps.ts), "r"(sb + OFF_XB + w * 4096),
                       "r"(32 * kg), "r"(0), "r"(8 * tn + 2 * w) : "memory");
          bulk_done_signal(&ws->cntT[32 * j]);
          asm volatile("mbarrier.arrive.shared::cluster.b64 _, [%0];" ::"r"(mapa(bars + 8 * B_RD0, rank ^ 1)) : "memory");
          if (t == 96) PROF_EV(13);
        }
        __syncwarp();
        if (j == 0) {
          hint_wait(&ws->cntH[0], (ep + 1) * 8u);
          const uint32_t t0 = (uint32_t)clock();
          float2 v;
          do { v = ld_x2((const float2*)ws->Ts + 2 * rb * 64 + t); spin_guard(t0); } while (__any_sync(0xffffffffu, (__float_as_uint(v.y) ^ tag) & 1));
          mbar_wait(bars + 8 * B_TL, 0);
          const uint32_t u = __float_as_uint(v.x);
          *(uint16_t*)(smem + OFF_T + t * 128 + ((t & 7) << 4)) = (uint16_t)u;
          *(uint16_t*)(smem + OFF_T + t * 128 + (((t & 7) ^ 1) << 4)) = (uint16_t)(u >> 16);
          asm volatile("fence.proxy.async.shared::cta;" ::: "memory");
          __syncwarp();
          mbar_arrive_if(lane == 0, bars + 8 * B_T);
        }
      }
    }
  } else {
    asm volatile("setmaxnreg.dec.sync.aligned.u32 24;");
    auto xf_load = [&](int q) {
      const uint32_t fb = bars + 8 * (B_FX + q);
      mbar_expect_tx(fb, U + 8192);
      tma3d(sb + q * U, &maps.x, fb, 64 * q, 0, 2 * rb);
      if (q >= 4) mbar_wait(bars + 8 * (B_FE + ((q - 4) >> 1)), 0);
      tma2d(sb + OFF_XB + (q & 3) * 8192, &maps.ft, fb, 64 * q, 64 * j);
    };
    if (elect_one()) {
      if (warp == 14) {
#pragma unroll
        for (int i = 2; i < B_FT; i++) mbar_init(bars + 8 * i, 1);
        asm volatile("fence.mbarrier_init.release.cluster;" ::: "memory");
        if (!helper) {
#pragma unroll 1
          for (int n = 0; n < 2; n++) {
            const uint32_t fb = bars + 8 * (B_FA + n);
            if (n) { xf_load(2); xf_load(3); }
            mbar_expect_tx(fb, U);
            tma2d(sb + OFF_RING + n * U, &maps.g64, fb, f_full, 64 * n);
            tma2d(sb + OFF_RING + n * U + 8192, &maps.u64, fb, f_full, 64 * n);
          }
        }
      } else if (warp == 15) {
#pragma unroll
        for (int i = B_FT; i < NBAR; i++) mbar_init(bars + 8 * i, i < B_EA ? 1 : i < B_T ? 2 : 4);
#pragma unroll
        for (int i = 0; i < 8; i++) mbar_expect_tx(bars + 8 * (B_Z + i), U / 2);
        asm volatile("fence.mbarrier_init.release.cluster;" ::: "memory");
        asm volatile("fence.proxy.async.shared::cta;" ::: "memory");
      }
    }
    __syncwarp();
    asm volatile("bar.arrive 0, 384;" ::: "memory");
    asm volatile("bar.arrive 4, 256;" ::: "memory");
    __syncwarp();
    asm volatile("barrier.cluster.arrive.relaxed.aligned;" ::: "memory");
    asm volatile("bar.sync 3, 128;" ::: "memory");
    if (warp == 15 && !helper) {
        mbar_wait(bars + 8 * B_FE, 0);
        const uint32_t tag = (ld_x1(&ws->epoch[blockIdx.x * 8]) + 1) & 1;
        const int c = lane >> 4, jj = 16 * blockIdx.x + (lane & 15), jm = (2048 - jj) & 2047;
        const unsigned short* pr = (const unsigned short*)w_r + 256 * c;
        const unsigned short* pi = (const unsigned short*)w_i + 256 * c;
        const float wr = 0.25f * (bf_lo(__ldg(pr + jj * 257)) + bf_lo(__ldg(pr + jm * 257)));
        const float wi = 0.25f * (bf_lo(__ldg(pi + jj * 257)) - bf_lo(__ldg(pi + jm * 257)));
        st_u2(ws->Wh + c * 2048 + jj, c ? pack_bf16(-wi, wr) : pack_bf16(wr, wi), tag);
        __syncwarp();
        hint_add_if(lane == 0, &ws->cntW[0]);
        mbar_wait(bars + 8 * B_XS, 0);
        const uint32_t t0 = (uint32_t)clock();
        uint4 v;
        do { v = ld_x4(ws->gate + rb * 128 + 4 * lane); spin_guard(t0); } while (__any_sync(0xffffffffu, ((v.x ^ tag) | (v.y ^ tag) | (v.z ^ tag) | (v.w ^ tag)) & 1));
        *(uint4*)(smem + OFF_G + lane * 16) = v;
        __syncwarp();
        mbar_arrive_if(lane < 4, bars + 8 * B_G);
      }
    auto part_load = [&](int i, unsigned ep1) {
      flag_wait(&ws->cntP[32 * (rb * 8 + j) + 8 * i], ep1 * 8u);
      mbar_wait(bars + 8 * (B_PZ + (i == 0)), 0);
      if (i == 2) PROF_EV(26);
      mbar_expect_tx(bars + 8 * (B_HP + i), U);
      bulk_load(sb + (i ? (i - 1) * U : OFF_T), ws->part + (size_t)((rb * 8 + j) * 3 + i) * 1024, U, bars + 8 * (B_HP + i));
    };
    if ((!helper || warp == 15) && elect_one()) {
      if (warp < 14) {
        const int p = warp - 12;
#pragma unroll 1
        for (int i = 4 + p; i < 13; i += 2) asm volatile("prefetch.tensormap [%0];" ::"l"((const char*)&maps + i * 128) : "memory");
#pragma unroll 1
        for (int n = 2; n < 31; n++) {
          const bool table = n == 4 || n >= 29;
          const bool half = n >= 17 && n < 21;
          const int q = n < 4 ? n : n < 17 ? n - 1 : n - 5;
          const CUtensorMap* m = table ? &maps.e : half ? &maps.g32 + p : &maps.g64 + p;
          const int c0 = table ? 0 : half ? f_half : f_full + 64 * (q >> 3);
          const int c1 = table ? (2 * rb + ((n & 1) ^ 1)) * 128 + 64 * p : half ? 128 * (n - 17) : 64 * (q & 7);
          const uint32_t fb = bars + 8 * (B_FA + (n & 3)), dst = sb + OFF_RING + (n & 3) * U + p * 8192;
          if (n < 4) mbar_wait(bars + 8 * (B_FE + n - 2), 0);
          else mbar_wait(bars + 8 * (B_EA + (n & 3)), ((n >> 2) & 1) ^ 1);
          tma2d(dst, m, fb, c0, c1);
          if (p == 0) mbar_expect_tx(fb, U);
        }
        mbar_wait(bars + 8 * (B_PZ + 1), 0);
        part_load(1 + p, ld_x1(&ws->epoch[blockIdx.x * 8]) + 1);
      } else if (warp == 15) {
        const unsigned ep1 = ld_x1(&ws->epoch[blockIdx.x * 8]) + 1;
        flag_wait(&ws->cntX[helper ? 0 : 32 * j], ep1 * 16u);
        PROF_EV(22);
        mbar_expect_tx(bars + 8 * B_HX, U);
        bulk_load(sb + OFF_XB, ws->X + (size_t)(helper ? 128 : kg * 8 + tn) * 8192, U, bars + 8 * B_HX);
        if (!helper) {
          flag_wait(&ws->cntT[32 * j], ep1 * 64u);
          PROF_EV(23);
          mbar_expect_tx(bars + 8 * B_TL, U);
          tma3d(sb + OFF_T, &maps.t, bars + 8 * B_TL, 64 * j, 0, 2 * rb);
          part_load(0, ep1);
          mbar_wait(bars + 8 * (B_HP + 1), 0); mbar_wait(bars + 8 * (B_HP + 2), 0);
          ws->epoch[blockIdx.x * 8] = ep1;
        }
      } else {
#pragma unroll 1
        for (int q = 4; q < 8; q++) xf_load(q);
        mbar_wait(bars + 8 * (B_FE + 2), 0);
        mbar_expect_tx(bars + 8 * B_E0, U);
        tma2d(sb + OFF_XB, &maps.e, bars + 8 * B_E0, 0, 2 * rb * 128);
        tma2d(sb + OFF_XB + 8192, &maps.e, bars + 8 * B_E0, 0, 2 * rb * 128 + 64);
#pragma unroll 1
        for (int h2 = 0; h2 < 2; h2++) {
          const int s0 = 2 * rb + h2, sg = (s0 & ~6) | ((s0 & 2) << 1) | ((s0 & 4) >> 1);
          mbar_wait(bars + 8 * (B_XS + h2), 0);
#pragma unroll 1
          for (int c = 0; c < 2; c++) {
            asm volatile("cp.async.bulk.tensor.4d.global.shared::cta.bulk_group [%0, {%2, %3, %4, %5}], [%1];" ::"l"(&maps.xs),
                         "r"(sb + OFF_XB + h2 * 8192 + c * 4096), "r"(0), "r"(sg), "r"(0), "r"(16 * j + 8 * c) : "memory");
            if (j == 0)
              asm volatile("cp.async.bulk.global.shared::cta.bulk_group [%0], [%1], 256;" ::"l"(ws->X + 128 * 8192 + c * 4096 + sg * 128),
                           "r"(sb + OFF_SP + h2 * 512 + c * 256) : "memory");
            if (SPACE && h2 + c < 2) __nanosleep(SPACE);
          }
        }
        bulk_done_signal(&ws->cntX[32 * j]);
        PROF_EV(20);
#pragma unroll 1
        for (int t = 0; t < 8; t++) {
          const int i = t < 3 ? t + 1 : t < 6 ? t - 2 : 0;
          const int col = 64 * (2 * ((q4 + i) & 3) + ((t < 3 || t == 6) ? 1 - rank : rank));
          const uint32_t fb = bars + 8 * (B_FT + (t & 3)), dst = sb + (t & 3) * TB;
          mbar_wait(bars + 8 * (B_ET + (t < 3 ? t + 1 : t & 3)), t >> 2);
          mbar_expect_tx(fb, TB);
          tma2d(dst, &maps.d224, fb, col, 224 * j);
          if (t < 2) mbar_wait(bars + 8 * (B_ET + t + 1), 0);
          tma2d(dst + 28672, &maps.ft, fb, col, 64 * j);
        }
      }
    }
  }
}

typedef CUresult (*EncodeFn)(CUtensorMap*, CUtensorMapDataType, cuuint32_t, void*, const cuuint64_t*, const cuuint64_t*, const cuuint32_t*,
                             const cuuint32_t*, CUtensorMapInterleave, CUtensorMapSwizzle, CUtensorMapL2promotion, CUtensorMapFloatOOBfill);

static void encode(EncodeFn f, CUtensorMap* m, const void* base, int rank, const cuuint64_t* dims, const cuuint64_t* strides, const cuuint32_t* box,
                   CUtensorMapSwizzle sw) {
  cuuint32_t es[5] = {1, 1, 1, 1, 1};
  f(m, CU_TENSOR_MAP_DATA_TYPE_BFLOAT16, rank, (void*)base, dims, strides, box, es, CU_TENSOR_MAP_INTERLEAVE_NONE, sw,
    CU_TENSOR_MAP_L2_PROMOTION_L2_128B, CU_TENSOR_MAP_FLOAT_OOB_FILL_NONE);
}

extern "C" void kernel_launch(void* const* d_in, const int* in_sizes, int n_in, void* d_out, int out_size) {
  (void)in_sizes; (void)n_in; (void)out_size;
  const __nv_bfloat16* x = (const __nv_bfloat16*)d_in[0];
  const __nv_bfloat16* w_r = (const __nv_bfloat16*)d_in[1];
  const __nv_bfloat16* w_i = (const __nv_bfloat16*)d_in[2];
  const __nv_bfloat16* Wg = (const __nv_bfloat16*)d_in[4];
  const __nv_bfloat16* Wu = (const __nv_bfloat16*)d_in[5];
  const __nv_bfloat16* Wd = (const __nv_bfloat16*)d_in[6];
  const __nv_bfloat16* gw = (const __nv_bfloat16*)d_in[7];

  void* fp = nullptr; cudaDriverEntryPointQueryResult qr;
  cudaGetDriverEntryPoint("cuTensorMapEncodeTiled", &fp, cudaEnableDefault, &qr);
  EncodeFn enc = (EncodeFn)fp;
  void *pFT, *pET, *pDT, *pW;
  cudaGetSymbolAddress(&pDT, g_DT); cudaGetSymbolAddress(&pW, g_work);
  void *pX = ((Work*)pW)->X, *pT = ((Work*)pW)->T;
  cudaGetSymbolAddress(&pFT, g_FT); cudaGetSymbolAddress(&pET, g_ET);

  Maps mp;
  const CUtensorMapSwizzle S128 = CU_TENSOR_MAP_SWIZZLE_128B, S64 = CU_TENSOR_MAP_SWIZZLE_64B;
  { cuuint64_t d[3] = {512, 64, 32}, s[2] = {32768, 1024}; cuuint32_t b[3] = {64, 64, 2}; encode(enc, &mp.x, x, 3, d, s, b, S128); }
  { cuuint64_t d[2] = {512, 512}, s[1] = {1024}; cuuint32_t b[2] = {64, 64}; encode(enc, &mp.ft, pFT, 2, d, s, b, S128); }
  { cuuint64_t d[4] = {128, 32, 2, 129}, s[3] = {256, 8192, 16384}; cuuint32_t b[4] = {128, 1, 2, 8}; encode(enc, &mp.xs, pX, 4, d, s, b, CU_TENSOR_MAP_SWIZZLE_NONE); }
  { cuuint64_t d[3] = {512, 32, 64}, s[2] = {65536, 1024}; cuuint32_t b[3] = {32, 32, 2}; encode(enc, &mp.ts, pT, 3, d, s, b, S64); }
  { cuuint64_t d[3] = {512, 64, 32}, s[2] = {1024, 65536}; cuuint32_t b[3] = {64, 64, 2}; encode(enc, &mp.t, pT, 3, d, s, b, S128); }
  { cuuint64_t d[2] = {64, 4096}, s[1] = {128}; cuuint32_t b[2] = {64, 64}; encode(enc, &mp.e, pET, 2, d, s, b, S128); }
  { cuuint64_t d[2] = {1792, 512}, s[1] = {3584}; cuuint32_t b[2] = {64, 64}, b2[2] = {32, 128};
    encode(enc, &mp.g64, Wg, 2, d, s, b, S128); encode(enc, &mp.u64, Wu, 2, d, s, b, S128);
    encode(enc, &mp.g32, Wg, 2, d, s, b2, S64); encode(enc, &mp.u32, Wu, 2, d, s, b2, S64); }
  { cuuint64_t d[2] = {512, 1792}, s[1] = {1024}; cuuint32_t b[2] = {64, 224}; encode(enc, &mp.d224, Wd, 2, d, s, b, S128); }
  { cuuint64_t d[4] = {264, 32, 8, 8}, s[3] = {32896, 512, 4112}; cuuint32_t b[4] = {24, 32, 2, 1};
    encode(enc, &mp.wr, w_r, 4, d, s, b, CU_TENSOR_MAP_SWIZZLE_NONE); encode(enc, &mp.wi, w_i, 4, d, s, b, CU_TENSOR_MAP_SWIZZLE_NONE); }

  cudaFuncSetAttribute(fused_kernel, cudaFuncAttributeMaxDynamicSharedMemorySize, SMEM_BYTES);
  fused_kernel<<<NCTA, 512, SMEM_BYTES>>>((Work*)pW, (const uint16_t*)pDT, w_r, w_i, gw, x, (__nv_bfloat16*)d_out, mp);
}
```

```cpp
#include <cuda_runtime.h>
#include <cuda_bf16.h>
#include <cuda.h>
#include <stdint.h>

namespace tbl {
constexpr double PI = 3.14159265358979323846264338327950288;
constexpr double sin_s(double x) { double t = x, s = x; for (int n = 1; n < 12; n++) { t *= -x * x / ((2 * n) * (2 * n + 1)); s += t; } return s; }
constexpr double cos_s(double x) { double t = 1, s = 1; for (int n = 1; n < 12; n++) { t *= -x * x / ((2 * n - 1) * (2 * n)); s += t; } return s; }
constexpr double cos2048(int m) {
  m &= 2047; if (m > 1024) m = 2048 - m;
  bool neg = false; if (m > 512) { m = 1024 - m; neg = true; }
  double v = (m <= 256) ? cos_s(2 * PI * m / 2048) : sin_s(2 * PI * (512 - m) / 2048);
  return neg ? -v : v;
}
constexpr uint16_t to_bf16(double v) {
  if (v == 0) return 0;
  uint16_t s = 0; if (v < 0) { s = 0x8000; v = -v; }
  int e = 0; while (v >= 2) { v /= 2; e++; } while (v < 1) { v *= 2; e--; }
  double m = (v - 1) * 128; int mi = (int)m; double fr = m - mi;
  if (fr > 0.5 || (fr == 0.5 && (mi & 1))) mi++;
  if (mi == 128) { mi = 0; e++; }
  return (uint16_t)(s | ((e + 127) << 7) | mi);
}
struct CosT { uint16_t v[2048]; constexpr CosT() : v() { for (int i = 0; i < 2048; i++) v[i] = to_bf16(cos2048(i)); } };
struct alignas(1024) FT {
  uint16_t v[512 * 512];
  constexpr FT() : v() {
    CosT c;
    for (int r = 0; r < 512; r++) {
      int k = (r >> 4) * 8 + (r & 7), e = (r >> 3) & 1;
      int mul = 4 * k, add = e ? 512 : 0;
      if (k == 0 && e == 1) { mul = 1024; add = 0; }
      for (int d = 0; d < 512; d++) v[r * 512 + d] = c.v[(d * mul + add) & 2047];
    }
  }
};
struct alignas(1024) ET {
  uint16_t v[2048 * 128];
  constexpr ET() : v() {
    CosT c;
    for (int s = 0; s < 2048; s++)
      for (int j = 0; j < 64; j++) {
        const int o = (s & 31) * 8192 + (s >> 5) * 64 + j;
        v[o] = c.v[(s * j) & 2047]; v[o + 4096] = c.v[(s * j + 512) & 2047];
      }
  }
};
struct alignas(1024) DT {
  uint16_t v[64 * 64];
  constexpr DT() : v() {
    CosT c;
    for (int r = 0; r < 64; r++)
      for (int n = 0; n < 64; n++) {
        const int sg = r >> 1, s0 = (sg & ~6) | ((sg & 2) << 1) | ((sg & 4) >> 1), e = r & 1, f = n & 1;
        const int m = 64 * s0 * (n >> 1) + (e == f ? 0 : e ? -512 : 512);
        v[r * 64 + (((n >> 3) ^ (r & 7)) << 3) + (n & 7)] = c.v[m & 2047];
      }
  }
};
}

__device__ constexpr tbl::FT g_FT = tbl::FT();
__device__ constexpr tbl::ET g_ET = tbl::ET();
__device__ constexpr tbl::DT g_DT = tbl::DT();

struct alignas(1024) Work {
  unsigned epoch[132 * 8];
  unsigned cntX[8 * 32], cntT[8 * 32], cntP[128 * 32], cntW[32], cntH[32];
  alignas(16) float gate[16 * 128];
  alignas(16) uint2 Wh[2 * 2048];
  alignas(16) uint2 Ts[32 * 64];
  alignas(1024) uint16_t X[129 * 8192];
  alignas(1024) uint16_t T[32 * 64 * 512];
  alignas(1024) uint4 part[128 * 3 * 1024];
};
__device__ Work g_work;
#define PROF_EV(i) do {} while (0)
#define PROF_CK(i) do {} while (0)

__device__ __forceinline__ uint32_t smem_u32(const void* p) { return (uint32_t)__cvta_generic_to_shared(p); }
__device__ __forceinline__ void mbar_init(uint32_t bar, uint32_t cnt) { asm volatile("mbarrier.init.shared::cta.b64 [%0], %1;" ::"r"(bar), "r"(cnt)); }
__device__ __forceinline__ void mbar_expect_tx(uint32_t bar, uint32_t bytes) { asm volatile("mbarrier.arrive.expect_tx.shared::cta.b64 _, [%0], %1;" ::"r"(bar), "r"(bytes) : "memory"); }
__device__ __forceinline__ void mbar_arrive(uint32_t bar) { asm volatile("mbarrier.arrive.shared::cta.b64 _, [%0];" ::"r"(bar) : "memory"); }
__device__ __forceinline__ bool elect_one() {
  uint32_t p;
  asm volatile("{\n.reg .pred p;\nelect.sync _|p, 0xffffffff;\nselp.u32 %0, 1, 0, p;\n}" : "=r"(p));
  return p;
}
__device__ __forceinline__ void mbar_arrive_if(bool p, uint32_t bar) {
  asm volatile("{\n.reg .pred p;\nsetp.ne.b32 p, %1, 0;\n@p mbarrier.arrive.shared::cta.b64 _, [%0];\n}" ::"r"(bar), "r"((int)p) : "memory");
}
__device__ __forceinline__ void hint_add_if(bool p, unsigned* a) {
  asm volatile("{\n.reg .pred p;\nsetp.ne.b32 p, %1, 0;\n@p red.relaxed.gpu.global.add.u32 [%0], 1;\n}" ::"l"(a), "r"((int)p) : "memory");
}
__device__ __forceinline__ bool mbar_try(uint32_t bar, uint32_t parity) {
  uint32_t ok;
  asm volatile("{\n.reg .pred p;\nmbarrier.test_wait.parity.shared::cta.b64 p, [%1], %2;\nselp.u32 %0, 1, 0, p;\n}" : "=r"(ok) : "r"(bar), "r"(parity) : "memory");
  return ok;
}
__device__ __forceinline__ void mbar_wait(uint32_t bar, uint32_t parity) {
  asm volatile(
      "{\n.reg .pred p;\n.reg .u32 n;\nmov.u32 n, 0;\n"
      "W_LOOP:\nmbarrier.try_wait.parity.shared::cta.b64 p, [%0], %1;\n@p bra W_DONE;\n"
      "add.u32 n, n, 1;\nsetp.lt.u32 p, n, 0x40000;\n@p bra W_LOOP;\ntrap;\nW_DONE:\n}" ::"r"(bar), "r"(parity) : "memory");
}
__device__ __forceinline__ void bulk_load(uint32_t dst, const void* src, uint32_t bytes, uint32_t bar) {
  asm volatile("cp.async.bulk.shared::cluster.global.mbarrier::complete_tx::bytes [%0], [%1], %2, [%3];" ::"r"(dst), "l"(src), "r"(bytes), "r"(bar) : "memory");
}
__device__ __forceinline__ void spin_guard(uint32_t t0) { if ((uint32_t)clock() - t0 > (1u << 30)) __trap(); }
__device__ __forceinline__ float2 ld_x2(const float2* p) { float2 v; asm volatile("ld.relaxed.gpu.global.v2.f32 {%0,%1}, [%2];" : "=f"(v.x), "=f"(v.y) : "l"(p) : "memory"); return v; }
__device__ __forceinline__ void st_u2(uint2* p, uint32_t a, uint32_t b) { asm volatile("st.relaxed.gpu.global.v2.u32 [%0], {%1,%2};" ::"l"(p), "r"(a), "r"(b) : "memory"); }
__device__ __forceinline__ uint32_t ld_x1(const void* p) { uint32_t v; asm volatile("ld.relaxed.gpu.global.u32 %0, [%1];" : "=r"(v) : "l"(p) : "memory"); return v; }
__device__ __forceinline__ uint4 ld_x4(const void* p) { uint4 v; asm volatile("ld.relaxed.gpu.global.v4.u32 {%0,%1,%2,%3}, [%4];" : "=r"(v.x), "=r"(v.y), "=r"(v.z), "=r"(v.w) : "l"(p) : "memory"); return v; }
__device__ __forceinline__ uint32_t mapa(uint32_t a, uint32_t cta) { uint32_t r; asm volatile("mapa.shared::cluster.u32 %0, %1, %2;" : "=r"(r) : "r"(a), "r"(cta)); return r; }
__device__ __forceinline__ void stsm4t(uint32_t a, uint32_t r0, uint32_t r1, uint32_t r2, uint32_t r3) {
  asm volatile("stmatrix.sync.aligned.m8n8.x4.trans.shared.b16 [%0], {%1,%2,%3,%4};" ::"r"(a), "r"(r0), "r"(r1), "r"(r2), "r"(r3) : "memory");
}
__device__ __forceinline__ void hint_add(unsigned* p) { asm volatile("red.relaxed.gpu.global.add.u32 [%0], 1;" ::"l"(p) : "memory"); }
__device__ __forceinline__ void hint_wait(const unsigned* p, unsigned target) {
  const uint32_t t0 = (uint32_t)clock();
  while ((int)(ld_x1(p) - target) < 0) spin_guard(t0);
}
__device__ __forceinline__ void bulk_done_signal(unsigned* p) {
  asm volatile("cp.async.bulk.commit_group;\ncp.async.bulk.wait_group 0;\nfence.proxy.async.global;" ::: "memory");
  hint_add(p);
}
__device__ __forceinline__ void flag_wait(const unsigned* p, unsigned target) {
  hint_wait(p, target);
  asm volatile("fence.proxy.async.global;" ::: "memory");
}
__device__ __forceinline__ void tma2d(uint32_t dst, const CUtensorMap* m, uint32_t bar, int c0, int c1) {
  asm volatile("cp.async.bulk.tensor.2d.shared::cluster.global.mbarrier::complete_tx::bytes [%0], [%1, {%3, %4}], [%2];" ::"r"(dst), "l"(m), "r"(bar), "r"(c0), "r"(c1) : "memory");
}
__device__ __forceinline__ void tma3d(uint32_t dst, const CUtensorMap* m, uint32_t bar, int c0, int c1, int c2) {
  asm volatile("cp.async.bulk.tensor.3d.shared::cluster.global.mbarrier::complete_tx::bytes [%0], [%1, {%3, %4, %5}], [%2];" ::"r"(dst), "l"(m), "r"(bar), "r"(c0), "r"(c1), "r"(c2) : "memory");
}
__device__ __forceinline__ void tma4d(uint32_t dst, const CUtensorMap* m, uint32_t bar, int c0, int c1, int c2, int c3) {
  asm volatile("cp.async.bulk.tensor.4d.shared::cluster.global.mbarrier::complete_tx::bytes [%0], [%1, {%3, %4, %5, %6}], [%2];" ::"r"(dst), "l"(m), "r"(bar), "r"(c0), "r"(c1), "r"(c2), "r"(c3) : "memory");
}
__device__ __forceinline__ void wg_fence() { asm volatile("wgmma.fence.sync.aligned;" ::: "memory"); }
__device__ __forceinline__ void wg_commit() { asm volatile("wgmma.commit_group.sync.aligned;" ::: "memory"); }
template <int N> __device__ __forceinline__ void wg_wait() { asm volatile("wgmma.wait_group.sync.aligned %0;" ::"n"(N) : "memory"); }
template <int O, int N, int NN> __device__ __forceinline__ void fence_regs(float (&d)[NN]) {
#pragma unroll
  for (int i = 0; i < N; i++) asm volatile("" : "+f"(d[O + i])::"memory");
}
__device__ __forceinline__ uint32_t pack_bf16(float lo, float hi) {
  uint32_t r; asm("cvt.rn.bf16x2.f32 %0, %1, %2;" : "=r"(r) : "f"(hi), "f"(lo)); return r;
}
__device__ __forceinline__ uint32_t pack_pin(float lo, float hi) {
  uint32_t r; asm volatile("cvt.rn.bf16x2.f32 %0, %1, %2;" : "=r"(r) : "f"(hi), "f"(lo) : "memory"); return r;
}
__device__ __forceinline__ uint32_t add_bf2(uint32_t a, uint32_t b) { uint32_t r; asm("add.rn.bf16x2 %0, %1, %2;" : "=r"(r) : "r"(a), "r"(b)); return r; }
__device__ __forceinline__ float bf_lo(uint32_t u) { return __uint_as_float(u << 16); }
__device__ __forceinline__ float bf_hi(uint32_t u) { return __uint_as_float(u & 0xffff0000u); }

__device__ __forceinline__ uint64_t d128(uint32_t lo) { uint64_t d; asm("mov.b64 %0, {%1, 0x40000040};" : "=l"(d) : "r"(lo)); return d; }
__device__ __forceinline__ uint64_t d64(uint32_t lo) { uint64_t d; asm("mov.b64 %0, {%1, 0x80000020};" : "=l"(d) : "r"(lo)); return d; }
template<int O,int TB,int ACC,int NN> __device__ __forceinline__ void mma_ss64(float (&d)[NN], uint64_t da, uint64_t db, int sd = 0){
  if constexpr (ACC == 1) asm volatile("wgmma.mma_async.sync.aligned.m64n64k16.f32.bf16.bf16 {%0,%1,%2,%3,%4,%5,%6,%7,%8,%9,%10,%11,%12,%13,%14,%15,%16,%17,%18,%19,%20,%21,%22,%23,%24,%25,%26,%27,%28,%29,%30,%31}, %32, %33, 1, 1, 1, %35, %34;"
   : "+f"(d[O+0]), "+f"(d[O+1]), "+f"(d[O+2]), "+f"(d[O+3]), "+f"(d[O+4]), "+f"(d[O+5]), "+f"(d[O+6]), "+f"(d[O+7]), "+f"(d[O+8]), "+f"(d[O+9]), "+f"(d[O+10]), "+f"(d[O+11]), "+f"(d[O+12]), "+f"(d[O+13]), "+f"(d[O+14]), "+f"(d[O+15]), "+f"(d[O+16]), "+f"(d[O+17]), "+f"(d[O+18]), "+f"(d[O+19]), "+f"(d[O+20]), "+f"(d[O+21]), "+f"(d[O+22]), "+f"(d[O+23]), "+f"(d[O+24]), "+f"(d[O+25]), "+f"(d[O+26]), "+f"(d[O+27]), "+f"(d[O+28]), "+f"(d[O+29]), "+f"(d[O+30]), "+f"(d[O+31])
   : "l"(da), "l"(db), "n"(TB & 1), "n"(TB >> 1));
  else if constexpr (ACC == 0) asm volatile("wgmma.mma_async.sync.aligned.m64n64k16.f32.bf16.bf16 {%0,%1,%2,%3,%4,%5,%6,%7,%8,%9,%10,%11,%12,%13,%14,%15,%16,%17,%18,%19,%20,%21,%22,%23,%24,%25,%26,%27,%28,%29,%30,%31}, %32, %33, 0, 1, 1, %35, %34;"
   : "=f"(d[O+0]), "=f"(d[O+1]), "=f"(d[O+2]), "=f"(d[O+3]), "=f"(d[O+4]), "=f"(d[O+5]), "=f"(d[O+6]), "=f"(d[O+7]), "=f"(d[O+8]), "=f"(d[O+9]), "=f"(d[O+10]), "=f"(d[O+11]), "=f"(d[O+12]), "=f"(d[O+13]), "=f"(d[O+14]), "=f"(d[O+15]), "=f"(d[O+16]), "=f"(d[O+17]), "=f"(d[O+18]), "=f"(d[O+19]), "=f"(d[O+20]), "=f"(d[O+21]), "=f"(d[O+22]), "=f"(d[O+23]), "=f"(d[O+24]), "=f"(d[O+25]), "=f"(d[O+26]), "=f"(d[O+27]), "=f"(d[O+28]), "=f"(d[O+29]), "=f"(d[O+30]), "=f"(d[O+31])
   : "l"(da), "l"(db), "n"(TB & 1), "n"(TB >> 1));
  else asm volatile("{\n.reg .pred p;\nsetp.ne.b32 p, %36, 0;\nwgmma.mma_async.sync.aligned.m64n64k16.f32.bf16.bf16 {%0,%1,%2,%3,%4,%5,%6,%7,%8,%9,%10,%11,%12,%13,%14,%15,%16,%17,%18,%19,%20,%21,%22,%23,%24,%25,%26,%27,%28,%29,%30,%31}, %32, %33, p, 1, 1, %35, %34;\n}"
   : "+f"(d[O+0]), "+f"(d[O+1]), "+f"(d[O+2]), "+f"(d[O+3]), "+f"(d[O+4]), "+f"(d[O+5]), "+f"(d[O+6]), "+f"(d[O+7]), "+f"(d[O+8]), "+f"(d[O+9]), "+f"(d[O+10]), "+f"(d[O+11]), "+f"(d[O+12]), "+f"(d[O+13]), "+f"(d[O+14]), "+f"(d[O+15]), "+f"(d[O+16]), "+f"(d[O+17]), "+f"(d[O+18]), "+f"(d[O+19]), "+f"(d[O+20]), "+f"(d[O+21]), "+f"(d[O+22]), "+f"(d[O+23]), "+f"(d[O+24]), "+f"(d[O+25]), "+f"(d[O+26]), "+f"(d[O+27]), "+f"(d[O+28]), "+f"(d[O+29]), "+f"(d[O+30]), "+f"(d[O+31])
   : "l"(da), "l"(db), "n"(TB & 1), "n"(TB >> 1), "r"(sd));
}
template<int O,int TB,int ACC,int NN> __device__ __forceinline__ void mma_rs64(float (&d)[NN], uint32_t a0, uint32_t a1, uint32_t a2, uint32_t a3, uint64_t db, int sd = 0){
  if constexpr (ACC == 1) asm volatile("wgmma.mma_async.sync.aligned.m64n64k16.f32.bf16.bf16 {%0,%1,%2,%3,%4,%5,%6,%7,%8,%9,%10,%11,%12,%13,%14,%15,%16,%17,%18,%19,%20,%21,%22,%23,%24,%25,%26,%27,%28,%29,%30,%31}, {%32,%33,%34,%35}, %36, 1, 1, 1, %37;"
   : "+f"(d[O+0]), "+f"(d[O+1]), "+f"(d[O+2]), "+f"(d[O+3]), "+f"(d[O+4]), "+f"(d[O+5]), "+f"(d[O+6]), "+f"(d[O+7]), "+f"(d[O+8]), "+f"(d[O+9]), "+f"(d[O+10]), "+f"(d[O+11]), "+f"(d[O+12]), "+f"(d[O+13]), "+f"(d[O+14]), "+f"(d[O+15]), "+f"(d[O+16]), "+f"(d[O+17]), "+f"(d[O+18]), "+f"(d[O+19]), "+f"(d[O+20]), "+f"(d[O+21]), "+f"(d[O+22]), "+f"(d[O+23]), "+f"(d[O+24]), "+f"(d[O+25]), "+f"(d[O+26]), "+f"(d[O+27]), "+f"(d[O+28]), "+f"(d[O+29]), "+f"(d[O+30]), "+f"(d[O+31])
   : "r"(a0), "r"(a1), "r"(a2), "r"(a3), "l"(db), "n"(TB));
  else if constexpr (ACC == 0) asm volatile("wgmma.mma_async.sync.aligned.m64n64k16.f32.bf16.bf16 {%0,%1,%2,%3,%4,%5,%6,%7,%8,%9,%10,%11,%12,%13,%14,%15,%16,%17,%18,%19,%20,%21,%22,%23,%24,%25,%26,%27,%28,%29,%30,%31}, {%32,%33,%34,%35}, %36, 0, 1, 1, %37;"
   : "=f"(d[O+0]), "=f"(d[O+1]), "=f"(d[O+2]), "=f"(d[O+3]), "=f"(d[O+4]), "=f"(d[O+5]), "=f"(d[O+6]), "=f"(d[O+7]), "=f"(d[O+8]), "=f"(d[O+9]), "=f"(d[O+10]), "=f"(d[O+11]), "=f"(d[O+12]), "=f"(d[O+13]), "=f"(d[O+14]), "=f"(d[O+15]), "=f"(d[O+16]), "=f"(d[O+17]), "=f"(d[O+18]), "=f"(d[O+19]), "=f"(d[O+20]), "=f"(d[O+21]), "=f"(d[O+22]), "=f"(d[O+23]), "=f"(d[O+24]), "=f"(d[O+25]), "=f"(d[O+26]), "=f"(d[O+27]), "=f"(d[O+28]), "=f"(d[O+29]), "=f"(d[O+30]), "=f"(d[O+31])
   : "r"(a0), "r"(a1), "r"(a2), "r"(a3), "l"(db), "n"(TB));
  else asm volatile("{\n.reg .pred p;\nsetp.ne.b32 p, %38, 0;\nwgmma.mma_async.sync.aligned.m64n64k16.f32.bf16.bf16 {%0,%1,%2,%3,%4,%5,%6,%7,%8,%9,%10,%11,%12,%13,%14,%15,%16,%17,%18,%19,%20,%21,%22,%23,%24,%25,%26,%27,%28,%29,%30,%31}, {%32,%33,%34,%35}, %36, p, 1, 1, %37;\n}"
   : "+f"(d[O+0]), "+f"(d[O+1]), "+f"(d[O+2]), "+f"(d[O+3]), "+f"(d[O+4]), "+f"(d[O+5]), "+f"(d[O+6]), "+f"(d[O+7]), "+f"(d[O+8]), "+f"(d[O+9]), "+f"(d[O+10]), "+f"(d[O+11]), "+f"(d[O+12]), "+f"(d[O+13]), "+f"(d[O+14]), "+f"(d[O+15]), "+f"(d[O+16]), "+f"(d[O+17]), "+f"(d[O+18]), "+f"(d[O+19]), "+f"(d[O+20]), "+f"(d[O+21]), "+f"(d[O+22]), "+f"(d[O+23]), "+f"(d[O+24]), "+f"(d[O+25]), "+f"(d[O+26]), "+f"(d[O+27]), "+f"(d[O+28]), "+f"(d[O+29]), "+f"(d[O+30]), "+f"(d[O+31])
   : "r"(a0), "r"(a1), "r"(a2), "r"(a3), "l"(db), "n"(TB), "r"(sd));
}
template<int O,int TB,int ACC,int NN> __device__ __forceinline__ void mma_ss128(float (&d)[NN], uint64_t da, uint64_t db, int sd = 0){
  if constexpr (ACC == 1) asm volatile("wgmma.mma_async.sync.aligned.m64n128k16.f32.bf16.bf16 {%0,%1,%2,%3,%4,%5,%6,%7,%8,%9,%10,%11,%12,%13,%14,%15,%16,%17,%18,%19,%20,%21,%22,%23,%24,%25,%26,%27,%28,%29,%30,%31,%32,%33,%34,%35,%36,%37,%38,%39,%40,%41,%42,%43,%44,%45,%46,%47,%48,%49,%50,%51,%52,%53,%54,%55,%56,%57,%58,%59,%60,%61,%62,%63}, %64, %65, 1, 1, 1, %67, %66;"
   : "+f"(d[O+0]), "+f"(d[O+1]), "+f"(d[O+2]), "+f"(d[O+3]), "+f"(d[O+4]), "+f"(d[O+5]), "+f"(d[O+6]), "+f"(d[O+7]), "+f"(d[O+8]), "+f"(d[O+9]), "+f"(d[O+10]), "+f"(d[O+11]), "+f"(d[O+12]), "+f"(d[O+13]), "+f"(d[O+14]), "+f"(d[O+15]), "+f"(d[O+16]), "+f"(d[O+17]), "+f"(d[O+18]), "+f"(d[O+19]), "+f"(d[O+20]), "+f"(d[O+21]), "+f"(d[O+22]), "+f"(d[O+23]), "+f"(d[O+24]), "+f"(d[O+25]), "+f"(d[O+26]), "+f"(d[O+27]), "+f"(d[O+28]), "+f"(d[O+29]), "+f"(d[O+30]), "+f"(d[O+31]), "+f"(d[O+32]), "+f"(d[O+33]), "+f"(d[O+34]), "+f"(d[O+35]), "+f"(d[O+36]), "+f"(d[O+37]), "+f"(d[O+38]), "+f"(d[O+39]), "+f"(d[O+40]), "+f"(d[O+41]), "+f"(d[O+42]), "+f"(d[O+43]), "+f"(d[O+44]), "+f"(d[O+45]), "+f"(d[O+46]), "+f"(d[O+47]), "+f"(d[O+48]), "+f"(d[O+49]), "+f"(d[O+50]), "+f"(d[O+51]), "+f"(d[O+52]), "+f"(d[O+53]), "+f"(d[O+54]), "+f"(d[O+55]), "+f"(d[O+56]), "+f"(d[O+57]), "+f"(d[O+58]), "+f"(d[O+59]), "+f"(d[O+60]), "+f"(d[O+61]), "+f"(d[O+62]), "+f"(d[O+63])
   : "l"(da), "l"(db), "n"(TB & 1), "n"(TB >> 1));
  else if constexpr (ACC == 0) asm volatile("wgmma.mma_async.sync.aligned.m64n128k16.f32.bf16.bf16 {%0,%1,%2,%3,%4,%5,%6,%7,%8,%9,%10,%11,%12,%13,%14,%15,%16,%17,%18,%19,%20,%21,%22,%23,%24,%25,%26,%27,%28,%29,%30,%31,%32,%33,%34,%35,%36,%37,%38,%39,%40,%41,%42,%43,%44,%45,%46,%47,%48,%49,%50,%51,%52,%53,%54,%55,%56,%57,%58,%59,%60,%61,%62,%63}, %64, %65, 0, 1, 1, %67, %66;"
   : "=f"(d[O+0]), "=f"(d[O+1]), "=f"(d[O+2]), "=f"(d[O+3]), "=f"(d[O+4]), "=f"(d[O+5]), "=f"(d[O+6]), "=f"(d[O+7]), "=f"(d[O+8]), "=f"(d[O+9]), "=f"(d[O+10]), "=f"(d[O+11]), "=f"(d[O+12]), "=f"(d[O+13]), "=f"(d[O+14]), "=f"(d[O+15]), "=f"(d[O+16]), "=f"(d[O+17]), "=f"(d[O+18]), "=f"(d[O+19]), "=f"(d[O+20]), "=f"(d[O+21]), "=f"(d[O+22]), "=f"(d[O+23]), "=f"(d[O+24]), "=f"(d[O+25]), "=f"(d[O+26]), "=f"(d[O+27]), "=f"(d[O+28]), "=f"(d[O+29]), "=f"(d[O+30]), "=f"(d[O+31]), "=f"(d[O+32]), "=f"(d[O+33]), "=f"(d[O+34]), "=f"(d[O+35]), "=f"(d[O+36]), "=f"(d[O+37]), "=f"(d[O+38]), "=f"(d[O+39]), "=f"(d[O+40]), "=f"(d[O+41]), "=f"(d[O+42]), "=f"(d[O+43]), "=f"(d[O+44]), "=f"(d[O+45]), "=f"(d[O+46]), "=f"(d[O+47]), "=f"(d[O+48]), "=f"(d[O+49]), "=f"(d[O+50]), "=f"(d[O+51]), "=f"(d[O+52]), "=f"(d[O+53]), "=f"(d[O+54]), "=f"(d[O+55]), "=f"(d[O+56]), "=f"(d[O+57]), "=f"(d[O+58]), "=f"(d[O+59]), "=f"(d[O+60]), "=f"(d[O+61]), "=f"(d[O+62]), "=f"(d[O+63])
   : "l"(da), "l"(db), "n"(TB & 1), "n"(TB >> 1));
  else asm volatile("{\n.reg .pred p;\nsetp.ne.b32 p, %68, 0;\nwgmma.mma_async.sync.aligned.m64n128k16.f32.bf16.bf16 {%0,%1,%2,%3,%4,%5,%6,%7,%8,%9,%10,%11,%12,%13,%14,%15,%16,%17,%18,%19,%20,%21,%22,%23,%24,%25,%26,%27,%28,%29,%30,%31,%32,%33,%34,%35,%36,%37,%38,%39,%40,%41,%42,%43,%44,%45,%46,%47,%48,%49,%50,%51,%52,%53,%54,%55,%56,%57,%58,%59,%60,%61,%62,%63}, %64, %65, p, 1, 1, %67, %66;\n}"
   : "+f"(d[O+0]), "+f"(d[O+1]), "+f"(d[O+2]), "+f"(d[O+3]), "+f"(d[O+4]), "+f"(d[O+5]), "+f"(d[O+6]), "+f"(d[O+7]), "+f"(d[O+8]), "+f"(d[O+9]), "+f"(d[O+10]), "+f"(d[O+11]), "+f"(d[O+12]), "+f"(d[O+13]), "+f"(d[O+14]), "+f"(d[O+15]), "+f"(d[O+16]), "+f"(d[O+17]), "+f"(d[O+18]), "+f"(d[O+19]), "+f"(d[O+20]), "+f"(d[O+21]), "+f"(d[O+22]), "+f"(d[O+23]), "+f"(d[O+24]), "+f"(d[O+25]), "+f"(d[O+26]), "+f"(d[O+27]), "+f"(d[O+28]), "+f"(d[O+29]), "+f"(d[O+30]), "+f"(d[O+31]), "+f"(d[O+32]), "+f"(d[O+33]), "+f"(d[O+34]), "+f"(d[O+35]), "+f"(d[O+36]), "+f"(d[O+37]), "+f"(d[O+38]), "+f"(d[O+39]), "+f"(d[O+40]), "+f"(d[O+41]), "+f"(d[O+42]), "+f"(d[O+43]), "+f"(d[O+44]), "+f"(d[O+45]), "+f"(d[O+46]), "+f"(d[O+47]), "+f"(d[O+48]), "+f"(d[O+49]), "+f"(d[O+50]), "+f"(d[O+51]), "+f"(d[O+52]), "+f"(d[O+53]), "+f"(d[O+54]), "+f"(d[O+55]), "+f"(d[O+56]), "+f"(d[O+57]), "+f"(d[O+58]), "+f"(d[O+59]), "+f"(d[O+60]), "+f"(d[O+61]), "+f"(d[O+62]), "+f"(d[O+63])
   : "l"(da), "l"(db), "n"(TB & 1), "n"(TB >> 1), "r"(sd));
}
template<int O,int TB,int ACC,int NN> __device__ __forceinline__ void mma_rs128(float (&d)[NN], uint32_t a0, uint32_t a1, uint32_t a2, uint32_t a3, uint64_t db, int sd = 0){
  if constexpr (ACC == 1) asm volatile("wgmma.mma_async.sync.aligned.m64n128k16.f32.bf16.bf16 {%0,%1,%2,%3,%4,%5,%6,%7,%8,%9,%10,%11,%12,%13,%14,%15,%16,%17,%18,%19,%20,%21,%22,%23,%24,%25,%26,%27,%28,%29,%30,%31,%32,%33,%34,%35,%36,%37,%38,%39,%40,%41,%42,%43,%44,%45,%46,%47,%48,%49,%50,%51,%52,%53,%54,%55,%56,%57,%58,%59,%60,%61,%62,%63}, {%64,%65,%66,%67}, %68, 1, 1, 1, %69;"
   : "+f"(d[O+0]), "+f"(d[O+1]), "+f"(d[O+2]), "+f"(d[O+3]), "+f"(d[O+4]), "+f"(d[O+5]), "+f"(d[O+6]), "+f"(d[O+7]), "+f"(d[O+8]), "+f"(d[O+9]), "+f"(d[O+10]), "+f"(d[O+11]), "+f"(d[O+12]), "+f"(d[O+13]), "+f"(d[O+14]), "+f"(d[O+15]), "+f"(d[O+16]), "+f"(d[O+17]), "+f"(d[O+18]), "+f"(d[O+19]), "+f"(d[O+20]), "+f"(d[O+21]), "+f"(d[O+22]), "+f"(d[O+23]), "+f"(d[O+24]), "+f"(d[O+25]), "+f"(d[O+26]), "+f"(d[O+27]), "+f"(d[O+28]), "+f"(d[O+29]), "+f"(d[O+30]), "+f"(d[O+31]), "+f"(d[O+32]), "+f"(d[O+33]), "+f"(d[O+34]), "+f"(d[O+35]), "+f"(d[O+36]), "+f"(d[O+37]), "+f"(d[O+38]), "+f"(d[O+39]), "+f"(d[O+40]), "+f"(d[O+41]), "+f"(d[O+42]), "+f"(d[O+43]), "+f"(d[O+44]), "+f"(d[O+45]), "+f"(d[O+46]), "+f"(d[O+47]), "+f"(d[O+48]), "+f"(d[O+49]), "+f"(d[O+50]), "+f"(d[O+51]), "+f"(d[O+52]), "+f"(d[O+53]), "+f"(d[O+54]), "+f"(d[O+55]), "+f"(d[O+56]), "+f"(d[O+57]), "+f"(d[O+58]), "+f"(d[O+59]), "+f"(d[O+60]), "+f"(d[O+61]), "+f"(d[O+62]), "+f"(d[O+63])
   : "r"(a0), "r"(a1), "r"(a2), "r"(a3), "l"(db), "n"(TB));
  else if constexpr (ACC == 0) asm volatile("wgmma.mma_async.sync.aligned.m64n128k16.f32.bf16.bf16 {%0,%1,%2,%3,%4,%5,%6,%7,%8,%9,%10,%11,%12,%13,%14,%15,%16,%17,%18,%19,%20,%21,%22,%23,%24,%25,%26,%27,%28,%29,%30,%31,%32,%33,%34,%35,%36,%37,%38,%39,%40,%41,%42,%43,%44,%45,%46,%47,%48,%49,%50,%51,%52,%53,%54,%55,%56,%57,%58,%59,%60,%61,%62,%63}, {%64,%65,%66,%67}, %68, 0, 1, 1, %69;"
   : "=f"(d[O+0]), "=f"(d[O+1]), "=f"(d[O+2]), "=f"(d[O+3]), "=f"(d[O+4]), "=f"(d[O+5]), "=f"(d[O+6]), "=f"(d[O+7]), "=f"(d[O+8]), "=f"(d[O+9]), "=f"(d[O+10]), "=f"(d[O+11]), "=f"(d[O+12]), "=f"(d[O+13]), "=f"(d[O+14]), "=f"(d[O+15]), "=f"(d[O+16]), "=f"(d[O+17]), "=f"(d[O+18]), "=f"(d[O+19]), "=f"(d[O+20]), "=f"(d[O+21]), "=f"(d[O+22]), "=f"(d[O+23]), "=f"(d[O+24]), "=f"(d[O+25]), "=f"(d[O+26]), "=f"(d[O+27]), "=f"(d[O+28]), "=f"(d[O+29]), "=f"(d[O+30]), "=f"(d[O+31]), "=f"(d[O+32]), "=f"(d[O+33]), "=f"(d[O+34]), "=f"(d[O+35]), "=f"(d[O+36]), "=f"(d[O+37]), "=f"(d[O+38]), "=f"(d[O+39]), "=f"(d[O+40]), "=f"(d[O+41]), "=f"(d[O+42]), "=f"(d[O+43]), "=f"(d[O+44]), "=f"(d[O+45]), "=f"(d[O+46]), "=f"(d[O+47]), "=f"(d[O+48]), "=f"(d[O+49]), "=f"(d[O+50]), "=f"(d[O+51]), "=f"(d[O+52]), "=f"(d[O+53]), "=f"(d[O+54]), "=f"(d[O+55]), "=f"(d[O+56]), "=f"(d[O+57]), "=f"(d[O+58]), "=f"(d[O+59]), "=f"(d[O+60]), "=f"(d[O+61]), "=f"(d[O+62]), "=f"(d[O+63])
   : "r"(a0), "r"(a1), "r"(a2), "r"(a3), "l"(db), "n"(TB));
  else asm volatile("{\n.reg .pred p;\nsetp.ne.b32 p, %70, 0;\nwgmma.mma_async.sync.aligned.m64n128k16.f32.bf16.bf16 {%0,%1,%2,%3,%4,%5,%6,%7,%8,%9,%10,%11,%12,%13,%14,%15,%16,%17,%18,%19,%20,%21,%22,%23,%24,%25,%26,%27,%28,%29,%30,%31,%32,%33,%34,%35,%36,%37,%38,%39,%40,%41,%42,%43,%44,%45,%46,%47,%48,%49,%50,%51,%52,%53,%54,%55,%56,%57,%58,%59,%60,%61,%62,%63}, {%64,%65,%66,%67}, %68, p, 1, 1, %69;\n}"
   : "+f"(d[O+0]), "+f"(d[O+1]), "+f"(d[O+2]), "+f"(d[O+3]), "+f"(d[O+4]), "+f"(d[O+5]), "+f"(d[O+6]), "+f"(d[O+7]), "+f"(d[O+8]), "+f"(d[O+9]), "+f"(d[O+10]), "+f"(d[O+11]), "+f"(d[O+12]), "+f"(d[O+13]), "+f"(d[O+14]), "+f"(d[O+15]), "+f"(d[O+16]), "+f"(d[O+17]), "+f"(d[O+18]), "+f"(d[O+19]), "+f"(d[O+20]), "+f"(d[O+21]), "+f"(d[O+22]), "+f"(d[O+23]), "+f"(d[O+24]), "+f"(d[O+25]), "+f"(d[O+26]), "+f"(d[O+27]), "+f"(d[O+28]), "+f"(d[O+29]), "+f"(d[O+30]), "+f"(d[O+31]), "+f"(d[O+32]), "+f"(d[O+33]), "+f"(d[O+34]), "+f"(d[O+35]), "+f"(d[O+36]), "+f"(d[O+37]), "+f"(d[O+38]), "+f"(d[O+39]), "+f"(d[O+40]), "+f"(d[O+41]), "+f"(d[O+42]), "+f"(d[O+43]), "+f"(d[O+44]), "+f"(d[O+45]), "+f"(d[O+46]), "+f"(d[O+47]), "+f"(d[O+48]), "+f"(d[O+49]), "+f"(d[O+50]), "+f"(d[O+51]), "+f"(d[O+52]), "+f"(d[O+53]), "+f"(d[O+54]), "+f"(d[O+55]), "+f"(d[O+56]), "+f"(d[O+57]), "+f"(d[O+58]), "+f"(d[O+59]), "+f"(d[O+60]), "+f"(d[O+61]), "+f"(d[O+62]), "+f"(d[O+63])
   : "r"(a0), "r"(a1), "r"(a2), "r"(a3), "l"(db), "n"(TB), "r"(sd));
}

#define NEARLY 0
#define XAHEAD 3
#define HEADN 6
#define WBATCH 1
#define WB 8
#define WSLEEP 20
#define XSPREAD 4
#define NOSEND 0
#define MSPLIT 2
#define PFALL 1
#define L2PF 0
#define STAG 0
#define EPF 2
#define XNB 2
#define FNB 0
#define GNB 0
#define TH 4
#define PF0 4
#define FSPLIT 1
#define MGLU 1
#define SPC 2
#define TL 14
#define GKB 4
#define T0A 8
#define TGATE 1
#define FIN32 1
#define SPACE 100
#define WPF 1
#define WAFTER 7
#define WPACE 0
#define GATE_AT 4
#define TPACE 40
#define PFMODE 0
#define MAPMODE 1
template <int V> struct IC { static constexpr int value = V; };
struct Maps { CUtensorMap x, ft, g64, u64, e, wr, wi, xs, ts, t, g32, u32, d224; };

constexpr int NCTA = 130;
constexpr int U = 16384;
constexpr int TB = 36864;
constexpr int OFF_RING = 8 * U, OFF_Z = 12 * U, OFF_XB = 12 * U, OFF_T = 13 * U, OFF_D = OFF_T;
constexpr int OFF_BAR = 14 * U, OFF_SP = OFF_BAR + 512, OFF_G = OFF_SP + 1024 + 128;
constexpr int SMEM_BYTES = OFF_G + 512;
constexpr int B_FX = 0, B_FA = 8, B_FT = 12, B_Z = 16, B_W = 24, B_HX = 25, B_TL = 26, B_HP = 27, B_WR = 30, B_E0 = 34;
constexpr int B_EA = 35, B_ET = 39, B_PZ = 43, B_RDY = 45, B_FE = 46;
constexpr int B_T = 50, B_XS = 51, B_G = 53, B_RD0 = 54, NBAR = 55;
__host__ __device__ constexpr int rslot(int n) { return n & 3; }
__host__ __device__ constexpr int rpar(int n) { return (n >> 2) & 1; }

__global__ void __cluster_dims__(2, 1, 1) __launch_bounds__(512, 1)
fused_kernel(Work* __restrict__ ws, const uint16_t* __restrict__ dtab, const __nv_bfloat16* __restrict__ w_r, const __nv_bfloat16* __restrict__ w_i,
             const __nv_bfloat16* __restrict__ gate_w, const __nv_bfloat16* __restrict__ x, __nv_bfloat16* __restrict__ out,
             const __grid_constant__ Maps maps) {
  extern __shared__ __align__(1024) uint8_t smem[];
  if (threadIdx.x < 32 && elect_one()) {
#pragma unroll
    for (int i = 0; i < PF0; i++) asm volatile("prefetch.tensormap [%0];" ::"l"((const char*)&maps + i * 128) : "memory");
  }
  const uint32_t sb = smem_u32(smem);
  const uint32_t bars = sb + OFF_BAR;
  const int tid = threadIdx.x, lane = tid & 31;
  const int warp = __shfl_sync(0xffffffffu, tid >> 5, 0);
  const bool helper = blockIdx.x >= 128;
  const int cl = (blockIdx.x >> 1) & 63, rank = blockIdx.x & 1;
  const int q4 = (cl & 1) | ((cl >> 2) & 2), rb = ((cl >> 1) & 3) | ((cl >> 4) << 2);
  const int j = 2 * q4 + rank;
  const int f_full = 448 * q4 + (rank ? 256 : 0);
  const int f_half = 448 * q4 + (rank ? 224 : 192);
  const int kg = 2 * j + (rb >> 3), tn = rb & 7;

  if (tid == 64) { PROF_EV(0); PROF_CK(40); }
  if (warp < 8) {
    if (!helper && tid < 32) {
      const int r = 16 * j + (tid & 15);
      asm volatile("prefetch.global.L2 [%0];" ::"l"(x + (size_t)(2 * rb + (r >> 6) + 32 * (r & 63)) * 512 + 64 * (tid >> 4)));
    }
    asm volatile("barrier.cluster.arrive.relaxed.aligned;" ::: "memory");
    asm volatile("setmaxnreg.inc.sync.aligned.u32 192;");
    if (!helper) {
      const int wg = warp >> 2, w = warp & 3, g = lane >> 2;
      const bool elect = (tid & 127) == 0;
      float cX[32], cA[64], cB[64], cC[64], ci[64], ct[64];
      const int zero = blockIdx.x >> 16;
      uint32_t h[56], yf[16];
      const uint32_t d0 = (sb & 0x3FFFF) >> 4;
      const uint32_t dK = d0 | (1u << 16), dN = d0 | (512u << 16);
      const uint32_t dX = dK + wg * 512;
      constexpr uint32_t RING = OFF_RING >> 4;
      auto waitA = [&](int n) { mbar_wait(bars + 8 * (B_FA + rslot(n)), rpar(n)); };
      auto freeA = [&](int n) { mbar_arrive_if(elect, bars + 8 * (B_EA + rslot(n))); };
      auto nop = [] {};

      asm volatile("bar.sync 0, 384;" ::: "memory");
#pragma unroll 1
      for (int i = 0; i < 4; i++) {
        const uint64_t dx = d128(dX + i * 2048), df = d128(dK + (OFF_XB >> 4) + (i & 1) * 1024);
        mbar_wait(bars + 8 * (B_FX + 2 * i), 0);
        wg_fence();
        mma_ss64<0, 0, 2>(cX, df, dx, i);
        mma_ss64<0, 0, 1>(cX, df + 2, dx + 2);
        wg_commit(); wg_wait<1>();
        mbar_arrive_if(elect && i, bars + 8 * (B_EA + rslot(i - 1)));
        mma_ss64<0, 0, 1>(cX, df + 4, dx + 4);
        mma_ss64<0, 0, 1>(cX, df + 6, dx + 6);
        if (i == 0 && tid == 0) PROF_EV(1);
        mbar_wait(bars + 8 * (B_FX + 2 * i + 1), 0);
        wg_fence();
#pragma unroll
        for (int k = 0; k < 4; k++) mma_ss64<0, 0, 1>(cX, df + (512 + k * 2), dx + (1024 + k * 2));
        wg_commit();
        waitA(i);
        wg_fence();
        const uint64_t da = d128(dX + i * 1024), db = d128(dN + RING + i * 1024);
        mma_ss128<0, 1, 2>(cA, da, db, i);
        wg_commit(); wg_wait<1>();
        mbar_arrive_if(elect, bars + 8 * (B_FE + i));
#pragma unroll
        for (int k = 1; k < 4; k++) mma_ss128<0, 1, 1>(cA, da + k * 2, db + k * 128);
        wg_commit();
      }
      fence_regs<0, 32>(cX);
#pragma unroll
      for (int e = 0; e < 16; e++) yf[e] = pack_pin(cX[2 * e], cX[2 * e + 1]);
      if (tid == 0) { PROF_EV(2); PROF_CK(42); }
      {
        waitA(4); mbar_wait(bars + 8 * B_E0, 0);
        const uint64_t de = d128(dN + (wg ? RING : OFF_XB >> 4));
        wg_fence();
        mma_rs128<0, 1, 0>(cB, yf[0], yf[1], yf[2], yf[3], de);
        wg_commit();
        wg_wait<1>();
        freeA(3);
#pragma unroll
        for (int k = 1; k < 4; k++) mma_rs128<0, 1, 1>(cB, yf[4 * k], yf[4 * k + 1], yf[4 * k + 2], yf[4 * k + 3], de + k * 128);
        wg_commit();
      }
      bool rel = false;
      auto acquire = [&](int n) {
        rel = elect;
        if (!mbar_try(bars + 8 * (B_FA + rslot(n)), rpar(n))) { wg_wait<0>(); freeA(n - 1); rel = false; waitA(n); }
      };
      auto freeP = [&](int n) { mbar_arrive_if(rel, bars + 8 * (B_EA + rslot(n - 1))); };
      auto ffn_step = [&](auto first, auto split, float (&acc)[64], int n, int kb, auto done, auto work) {
        constexpr int SPLIT = decltype(split)::value;
        acquire(n);
        wg_fence();
        const uint64_t dx = d128(dX + kb * 1024), db = d128(dN + RING + rslot(n) * 1024);
        mma_ss128<0, 1, decltype(first)::value>(acc, dx, db, kb);
#pragma unroll
        for (int k = 1; k < SPLIT; k++) mma_ss128<0, 1, 1>(acc, dx + k * 2, db + k * 128);
        wg_commit();
        work();
        wg_wait<1>();
        freeP(n);
        done();
        if (SPLIT < 4) {
          wg_fence();
#pragma unroll
          for (int k = SPLIT; k < 4; k++) mma_ss128<0, 1, 1>(acc, dx + k * 2, db + k * 128);
          wg_commit();
        }
      };
      {
        const int s0 = 2 * rb + wg, kr = 2 * ((s0 & 1) | ((s0 & 4) >> 1));
        const int m = lane >> 3, r = lane & 7;
        const uint32_t a0 = sb + OFF_XB + wg * 8192 + (((w >> 1) * 8 + (m >> 1)) * 2 + (w & 1)) * 256 + (m & 1) * 128 + ((r ^ (kr + (m & 1))) << 4);
        ffn_step(IC<1>(), IC<4>(), cA, 5, 4, [&] { fence_regs<0, 64>(cB); }, nop);
        asm volatile("bar.sync 5, 256;" ::: "memory");
        auto stage = [&](int i) {
          stsm4t(a0 + i * 1024, pack_bf16(cB[8 * i] - cB[34 + 8 * i], cB[8 * i + 1] - cB[35 + 8 * i]),
                 pack_bf16(cB[32 + 8 * i] + cB[8 * i + 2], cB[33 + 8 * i] + cB[8 * i + 3]),
                 pack_bf16(cB[8 * i + 4] - cB[38 + 8 * i], cB[8 * i + 5] - cB[39 + 8 * i]),
                 pack_bf16(cB[36 + 8 * i] + cB[8 * i + 6], cB[37 + 8 * i] + cB[8 * i + 7]));
          if (j == 0 && w == 0) {
            const uint32_t a1 = r ? sb + OFF_SP + 1024 : sb + OFF_SP + wg * 512 + (m & 1) * 256 + (m >> 1) * 128;
#pragma unroll
            for (int n = 2 * i; n < 2 * i + 2; n++)
              asm volatile("stmatrix.sync.aligned.m8n8.x4.shared.b16 [%0], {%1,%2,%3,%4};" ::"r"(a1 + ((n ^ (kr + (m >> 1)) ^ r) << 4)),
                           "r"(pack_bf16(cB[4 * n], cB[4 * n + 1])), "r"(pack_bf16(cB[4 * n + 2], cB[4 * n + 3])),
                           "r"(pack_bf16(cB[32 + 4 * n], cB[33 + 4 * n])), "r"(pack_bf16(cB[34 + 4 * n], cB[35 + 4 * n])) : "memory");
          }
        };
        auto publish = [&] {
          asm volatile("fence.proxy.async.shared::cta;" ::: "memory");
          __syncwarp();
          mbar_arrive_if(lane == 0, bars + 8 * (B_XS + wg));
          if (tid == 0) PROF_EV(3);
        };
        stage(0);
        ffn_step(IC<1>(), IC<FSPLIT>(), cA, 6, 5, nop, nop);
        stage(1);
        ffn_step(IC<1>(), IC<FSPLIT>(), cA, 7, 6, nop, nop);
        stage(2);
        ffn_step(IC<1>(), IC<2>(), cA, 8, 7, [&] { stage(3); }, nop);
        publish();
      }
      uint32_t gb0 = 0, gb1 = 0;
      uint32_t ob[2] = {0, 0};
      auto glu = [&](auto& acc, int half, int ho, int i0, int i1) {
#pragma unroll
        for (int i = i0; i < i1; i++)
          asm volatile("{\n.reg .b32 a, b;\ncvt.rn.relu.bf16x2.f32 a, %2, %1;\ncvt.rn.bf16x2.f32 b, %4, %3;\nmul.rn.bf16x2 a, a, b;\nmul.rn.bf16x2 %0, a, %5;\n}"
                       : "=r"(h[ho + i]) : "f"(acc[2 * i]), "f"(acc[2 * i + 1]), "f"(acc[half + 2 * i]), "f"(acc[half + 1 + 2 * i]), "r"(ob[i & 1]) : "memory");
      };
      ffn_step(IC<2>(), IC<1>(), cB, 9, zero, nop, nop);
#pragma unroll 1
      for (int kb = 1; kb < 8; kb++)
        ffn_step(IC<1>(), IC<FSPLIT>(), cB, 9 + kb, kb, nop, [&] {
          if (kb == GKB) {
            mbar_wait(bars + 8 * B_G, 0);
            asm volatile("ld.shared.u32 %0, [%2];\nld.shared.u32 %1, [%2+32];" : "=r"(gb0), "=r"(gb1) : "r"(sb + OFF_G + (wg * 64 + w * 16 + g) * 4) : "memory");
          } else if (kb == 5 + 2 * wg) {
            ob[0] = pack_bf16(1.0f - bf_hi(gb0), 1.0f - bf_hi(gb0)); ob[1] = pack_bf16(1.0f - bf_hi(gb1), 1.0f - bf_hi(gb1));
            glu(cA, 32, 0, 0, 16);
          }
        });
      const uint32_t tag = gb0 & 1;
      const float g0 = bf_hi(gb0), g1 = bf_hi(gb1);
      if (tid == 0) { PROF_EV(4); PROF_CK(43); }
      auto m_step = [&](auto first, int i) {
        acquire(17 + i);
        wg_fence();
        const uint64_t dx = d128(dX + i * 2048), dm = d64(dN + RING + rslot(17 + i) * 1024);
        mma_ss64<0, 1, decltype(first)::value>(ct, dx, dm);
#pragma unroll
        for (int k = 1; k < MSPLIT; k++) mma_ss64<0, 1, 1>(ct, dx + ((k >> 2) * 1024 + (k & 3) * 2), dm + k * 64);
        wg_commit();
        wg_wait<1>();
        freeP(17 + i);
        wg_fence();
#pragma unroll
        for (int k = MSPLIT; k < 8; k++) mma_ss64<0, 1, 1>(ct, dx + ((k >> 2) * 1024 + (k & 3) * 2), dm + k * 64);
        wg_commit();
      };
      m_step(IC<0>(), 0);
#pragma unroll 1
      for (int i = 1; i < 5; i++) {
        if (i == 1 + 2 * wg) glu(cB, 32, 16, 0, 16);
        if (i < 4) m_step(IC<1>(), i);
      }
      if (tid == 0) { PROF_EV(5); PROF_CK(44); }
      ffn_step(IC<0>(), IC<1>(), cC, 21, 0, nop, nop);
#pragma unroll 1
      for (int kb = 1; kb < 8; kb++)
        ffn_step(IC<1>(), IC<FSPLIT>(), cC, 21 + kb, kb, [&] { mbar_arrive_if(elect && !(kb & 1), bars + 8 * (B_ET + (kb >> 1) - 1)); }, [&] {
          if (kb == 1 + wg) glu(ct, 16, 48, 0, 8);
        });

      auto twait = [&](uint32_t bar, uint32_t par, int) { mbar_wait(bar, par); };
      const int fo = warp * 128 + lane;
      auto fetch = [&](uint4 (&pv)[4], int z) {
        twait(bars + 8 * (z < 4 ? B_Z + 2 * z + wg : B_HP + z - 4), 0, 8 + z);
        const uint8_t* src = smem + (z < 4 ? OFF_Z - z * U : z == 4 ? OFF_T : (z - 5) * U) + fo * 16;
#pragma unroll
        for (int i = 0; i < 4; i++) pv[i] = *(const uint4*)(src + i * 512);
      };
      const uint32_t peerZ = mapa(sb + OFF_Z + fo * 16, rank ^ 1), peerB = mapa(bars + 8 * (B_Z + wg), rank ^ 1);
      auto tile_mma = [&](auto off, int t, int k0, int k1, int init) {
        constexpr int O = decltype(off)::value;
        const uint64_t db = d128(dN + (t & 3) * (TB >> 4)), dw = db + rank * 256, dm = db + (rank ? 0 : 1536);
#pragma unroll
        for (int k = k0; k < k1; k++) {
          if (k == 0) mma_rs64<O, 1, 2>(ct, h[0], h[1], h[2], h[3], dw, init);
          else if (k < 14) mma_rs64<O, 1, 1>(ct, h[4 * k], h[4 * k + 1], h[4 * k + 2], h[4 * k + 3], k < 12 ? dw + k * 128 : dm + (k - 12) * 128);
          else mma_rs64<O, 1, 1>(ct, yf[4 * k - 56], yf[4 * k - 55], yf[4 * k - 54], yf[4 * k - 53], db + k * 128);
        }
      };
      uint4 pv[4] = {};
      auto tile = [&](auto off, int t) {
        constexpr int P = 32 - decltype(off)::value;
        const bool grid = t >= 4 && t < 7, pre = t >= 3 && t != 6;
        const int zo = grid ? t - 4 : t == 7 ? 3 : t - 1, z = t - 3;
        const int owner = rb * 8 + 2 * ((q4 + zo + 1) & 3) + rank;
        uint4* dst = ws->part + (size_t)(owner * 3 + zo) * 1024 + fo;
        const uint32_t src = sb + (z < 4 ? OFF_Z - z * U : OFF_T) + fo * 16;
        twait(bars + 8 * (B_FT + (t & 3)), t >> 2, t);
        wg_fence();
        tile_mma(off, t, 0, TH, zero);
        wg_commit();
        wg_wait<1>();
        mbar_arrive_if(elect && t < 6, bars + 8 * (B_ET + t - 1));
        if (t < 3) twait(bars + 8 * (t == 1 ? B_RD0 : B_RDY), 0, 14 + t);
        fence_regs<P, 32>(ct);
#pragma unroll
        for (int i = 0; i < 4; i++) {
          pv[i].x = (add_bf2(pv[i].x, pack_bf16(ct[P + 8 * i], ct[P + 8 * i + 1])) & ~(uint32_t)grid) | (tag & grid);
          pv[i].y = add_bf2(pv[i].y, pack_bf16(ct[P + 8 * i + 2], ct[P + 8 * i + 3]));
          pv[i].z = add_bf2(pv[i].z, pack_bf16(ct[P + 8 * i + 4], ct[P + 8 * i + 5]));
          pv[i].w = add_bf2(pv[i].w, pack_bf16(ct[P + 8 * i + 6], ct[P + 8 * i + 7]));
        }
        if (grid) {
#pragma unroll
          for (int i = 0; i < 4; i++)
            asm volatile("st.relaxed.gpu.global.v4.u32 [%0], {%1,%2,%3,%4};" ::"l"(dst + i * 32), "r"(pv[i].x), "r"(pv[i].y), "r"(pv[i].z), "r"(pv[i].w) : "memory");
          hint_add_if(lane == 0, &ws->cntP[32 * owner + 8 * zo]);
        }
        auto share = [&](int i) {
          asm volatile("st.async.weak.shared::cluster.mbarrier::complete_tx::bytes.v4.b32 [%0], {%2,%3,%4,%5}, [%1];" ::"r"(peerZ - zo * U + i * 512),
                       "r"(peerB + 16 * zo), "r"(pv[i].x), "r"(pv[i].y), "r"(pv[i].z), "r"(pv[i].w) : "memory");
        };
        if (P == 0 && t == 7) { share(1); share(2); share(3); }
#pragma unroll
        for (int i = 0; i < 4; i++) {
          if (i == 0 ? !grid : t < 4) share(i);
          wg_fence();
          tile_mma(off, t, TH + SPC * i, i < 3 ? TH + SPC * i + SPC : TL, 0);
        }
        wg_commit();
        if (pre) twait(bars + 8 * (z < 4 ? B_Z + 2 * z + wg : B_HP), 0, 8 + z);
        wg_fence();
#pragma unroll
        for (int i = 0; i < 4; i++) {
          asm volatile("{\n.reg .pred p;\nsetp.ne.b32 p, %5, 0;\nmov.b32 %0, 0;\nmov.b32 %1, 0;\nmov.b32 %2, 0;\nmov.b32 %3, 0;\n@p ld.shared.v4.u32 {%0,%1,%2,%3}, [%4];\n}"
                       : "=r"(pv[i].x), "=r"(pv[i].y), "=r"(pv[i].z), "=r"(pv[i].w) : "r"(src + i * 512), "r"((int)pre) : "memory");
          tile_mma(off, t, TL + i, i < 3 ? TL + 1 + i : 18, 0);
        }
        wg_commit();
      };
      asm volatile("barrier.cluster.wait.aligned;" ::: "memory");
      twait(bars + 8 * B_FT, 0, 0);
      wg_fence();
      tile_mma(IC<0>(), 0, 0, T0A, zero);
      wg_commit();
      waitA(29 + wg);
      wg_wait<1>();
      mbar_arrive_if(elect, bars + 8 * (B_ET + 3));
      glu(cC, 32, 32, 0, 16);
      if (tid == 0) PROF_EV(6);
      if (tid == 128) PROF_EV(27);
      mbar_wait(bars + 8 * (j == 0 ? B_T : B_TL), 0);
      if (tid == 0) { PROF_EV(7); PROF_CK(45); }
      wg_fence();
      {
        const uint64_t dt = d128(dN + (OFF_T >> 4) + wg * 512), de = d128(dK + RING + (1 + wg) * 1024);
        mma_ss64<0, 1, 0>(ci, de, dt);
        mma_ss64<32, 1, 0>(ci, de + 512, dt);
#pragma unroll
        for (int k = 1; k < 4; k++) {
          mma_ss64<0, 1, 1>(ci, de + k * 2, dt + k * 128);
          mma_ss64<32, 1, 1>(ci, de + (512 + k * 2), dt + k * 128);
        }
        wg_commit();
      }
      tile_mma(IC<0>(), 0, T0A, 14, 0);
      wg_commit();
      wg_wait<1>();
      if (elect) asm volatile("mbarrier.arrive.shared::cluster.b64 _, [%0];" ::"r"(mapa(bars + 8 * B_RDY, rank ^ 1)) : "memory");
      mbar_arrive_if(elect, bars + 8 * (B_PZ + 1));
      fence_regs<0, 64>(ci);
#pragma unroll
      for (int i = 0; i < 16; i++) {
        const float gg = ((i & 1) ? g1 : g0) * (2.0f / (2048.0f * 512.0f));
        if (i & 2) yf[i] = pack_pin((ci[2 * i] - ci[28 + 2 * i]) * gg, (ci[2 * i + 1] - ci[29 + 2 * i]) * gg);
        else yf[i] = pack_pin((ci[2 * i] + ci[36 + 2 * i]) * gg, (ci[2 * i + 1] + ci[37 + 2 * i]) * gg);
      }
      wg_fence();
      tile_mma(IC<0>(), 0, 14, 18, 0);
      wg_commit();
      if (tid == 0) PROF_EV(8);
      if (tid == 128) PROF_EV(28);
#pragma unroll 1
      for (int t = 1;; t += 2) {
        tile(IC<32>(), t);
        if (t == 7) break;
        tile(IC<0>(), t + 1);
      }
      if (tid == 0) { PROF_EV(9); PROF_CK(46); }
      if (tid == 128) PROF_EV(29);
      {
        uint4 p1[4], p2[4];
        auto acc4 = [&](uint4 (&d)[4], const uint4 (&a)[4]) {
#pragma unroll
          for (int i = 0; i < 4; i++) { d[i].x = add_bf2(d[i].x, a[i].x); d[i].y = add_bf2(d[i].y, a[i].y); d[i].z = add_bf2(d[i].z, a[i].z); d[i].w = add_bf2(d[i].w, a[i].w); }
        };
        uint4 p3[4];
        fetch(p1, 5);
        fetch(p2, 3);
        if (tid == 0) PROF_EV(25);
        wg_wait<0>();
        fence_regs<32, 32>(ct);
        fetch(p3, 6);
        if (tid == 0) PROF_EV(24);
        {
          auto stale = [&] {
            uint32_t bad = 0;
#pragma unroll
            for (int i = 0; i < 4; i++) bad |= (pv[i].x ^ tag) | (p1[i].x ^ tag) | (p3[i].x ^ tag);
            return __any_sync(0xffffffffu, bad & 1);
          };
          if (__builtin_expect(stale(), 0)) {
            const uint4* src = ws->part + (size_t)(rb * 8 + j) * 3 * 1024 + fo;
            int n = 0;
            do {
#pragma unroll
              for (int i = 0; i < 4; i++) { pv[i] = ld_x4(src + i * 32); p1[i] = ld_x4(src + 1024 + i * 32); p3[i] = ld_x4(src + 2048 + i * 32); }
              if (++n > (1 << 21)) __trap();
            } while (stale());
          }
#pragma unroll
          for (int i = 0; i < 4; i++) { pv[i].x &= ~1u; p1[i].x &= ~1u; p3[i].x &= ~1u; }
        }
        acc4(pv, p1); acc4(p2, p3);
#pragma unroll
        for (int i = 0; i < 4; i++) {
          pv[i].x = pack_bf16(ct[32 + 8 * i] + bf_lo(pv[i].x) + bf_lo(p2[i].x), ct[33 + 8 * i] + bf_hi(pv[i].x) + bf_hi(p2[i].x));
          pv[i].y = pack_bf16(ct[34 + 8 * i] + bf_lo(pv[i].y) + bf_lo(p2[i].y), ct[35 + 8 * i] + bf_hi(pv[i].y) + bf_hi(p2[i].y));
          pv[i].z = pack_bf16(ct[36 + 8 * i] + bf_lo(pv[i].z) + bf_lo(p2[i].z), ct[37 + 8 * i] + bf_hi(pv[i].z) + bf_hi(p2[i].z));
          pv[i].w = pack_bf16(ct[38 + 8 * i] + bf_lo(pv[i].w) + bf_lo(p2[i].w), ct[39 + 8 * i] + bf_hi(pv[i].w) + bf_hi(p2[i].w));
        }
        if (tid == 0) PROF_EV(14);
        const uint32_t stg = sb + OFF_T + warp * 2048;
        const int mr = (lane & 7) + ((lane >> 3) & 1) * 8, mc = lane >> 4;
#pragma unroll
        for (int i = 0; i < 4; i++)
          asm volatile("stmatrix.sync.aligned.m8n8.x4.shared.b16 [%0], {%1,%2,%3,%4};" ::"r"(stg + mr * 128 + (((2 * i + mc) ^ (mr & 7)) << 4)), "r"(pv[i].x),
                       "r"(pv[i].y), "r"(pv[i].z), "r"(pv[i].w) : "memory");
        __syncwarp();
#pragma unroll
        for (int i = 0; i < 4; i++) {
          const int r = 4 * i + (lane >> 3), c = lane & 7;
          const uint4 v = *(const uint4*)(smem + OFF_T + warp * 2048 + r * 128 + ((c ^ (r & 7)) << 4));
          *(uint4*)(out + (size_t)(2 * rb + wg + 32 * (16 * w + r)) * 512 + 64 * j + 8 * c) = v;
        }
      }
      if (tid == 0) { PROF_EV(15); PROF_CK(41); }
      if (tid == 128) PROF_EV(30);
    }
  } else if (warp < 12) {
    asm volatile("setmaxnreg.dec.sync.aligned.u32 104;");
    asm volatile("barrier.cluster.arrive.relaxed.aligned;" ::: "memory");
    const int t = tid - 256, w = warp - 8;
    const uint32_t ep = ld_x1(&ws->epoch[blockIdx.x * 8]);
    const uint32_t tag = (ep + 1) & 1;
    auto w_issue = [&](const CUtensorMap* m) {

      if (elect_one()) { mbar_expect_tx(bars + 8 * (B_WR + w), 3072); tma4d(sb + OFF_T + w * 3072, m, bars + 8 * (B_WR + w), 16 * kg, 0, 2 * w, tn); }

          __syncwarp();
    };
    auto gate_rows = [&] {
      const int r = 16 * j + 4 * w + (lane >> 3);
      const uint4* pg = (const uint4*)gate_w + (lane & 7);
      {
        float a = 0.f;
        asm volatile("bar.sync 4, 256;" ::: "memory");
#pragma unroll 1
        for (int hf = 0; hf < 2; hf++) {
          uint4 v[4], u[4];
#pragma unroll
          for (int kb = 0; kb < 4; kb++) v[kb] = __ldg(pg + (4 * hf + kb) * 8);
          mbar_wait(bars + 8 * (B_FE + 1 + 2 * hf), 0);
          if (hf) w_issue(&maps.wr);
#pragma unroll
          for (int kb = 0; kb < 4; kb++) u[kb] = *(const uint4*)(smem + (4 * hf + kb) * U + r * 128 + (((lane ^ r) & 7) << 4));
#pragma unroll
          for (int kb = 0; kb < 4; kb++) {
            const uint32_t uu[4] = {u[kb].x, u[kb].y, u[kb].z, u[kb].w}, vv[4] = {v[kb].x, v[kb].y, v[kb].z, v[kb].w};
#pragma unroll
            for (int e = 0; e < 4; e++) {
              uint32_t pr;
              asm("mul.rn.bf16x2 %0, %1, %2;" : "=r"(pr) : "r"(uu[e]), "r"(vv[e]));
              a += bf_lo(pr) + bf_hi(pr);
            }
          }
        }
#pragma unroll
        for (int o = 4; o; o >>= 1) a += __shfl_xor_sync(0xffffffffu, a, o);
        if ((lane & 7) == 0)
          asm volatile("st.relaxed.gpu.global.u32 [%0], %1;" ::"l"(ws->gate + rb * 128 + r),
                       "r"(pack_bf16(0.f, __fdividef(1.0f, 1.0f + __expf(-bf_lo(pack_bf16(a, 0.f))))) | tag) : "memory");
        if (t == 0) PROF_EV(18);
      }
    };
    {
      const int g = lane >> 2, q = lane & 3;
      uint32_t wf[32];
      if (!helper) {
        gate_rows();
        const uint32_t wa = sb + OFF_T + w * (3072 + 4) + q * 48 + g * 2;
#pragma unroll 1
        for (int ri = 0; ri < 2; ri++) {
          mbar_wait(bars + 8 * (B_WR + w), ri);
#pragma unroll
          for (int n2 = 0; n2 < 32 / WB; n2++) {
            uint32_t v[WB];
#pragma unroll
            for (int i = 0; i < WB; i++) {
              const int e = n2 * WB + i;
              asm volatile("ld.shared.u16 %0, [%1];" : "=r"(v[i]) : "r"(wa + ((e >> 1) & 7) * 192 + (e & 1) * (1536 + 2) + (e >> 4) * 16) : "memory");
            }
#pragma unroll
            for (int i = 0; i < WB; i++) wf[n2 * WB + i] = __byte_perm(wf[n2 * WB + i], v[i], 0x5432);
            if (WSLEEP) { asm volatile("nanosleep.u32 %0;" ::"r"(WSLEEP + (v[WB - 1] >> 16)) : "memory"); }
          }
          __syncwarp();
          if (ri == 0) w_issue(&maps.wi);
        }
        asm volatile("bar.sync 1, 128;" ::: "memory");
        if (t == 0) PROF_EV(11);
      } else {
        asm volatile("bar.sync 4, 256;" ::: "memory");
        hint_wait(&ws->cntW[0], (ep + 1) * 128u);
        const uint32_t t0 = (uint32_t)clock();
#pragma unroll 1
        for (;;) {
          uint32_t bad = 0;
#pragma unroll
          for (int i = 0; i < 32; i++) {
            const float2 v = ld_x2((const float2*)ws->Wh + (i >> 4) * 2048 + 16 * w + g + 8 * (i & 1) + 64 * q + ((i >> 1) & 7) * 256);
            wf[i] = __float_as_uint(v.x); bad |= __float_as_uint(v.y) ^ tag;
          }
          if (!__any_sync(0xffffffffu, bad & 1)) break;
          spin_guard(t0);
        }
        if (t == 0) PROF_EV(11);
      }
      if (w == 0 && elect_one()) { mbar_expect_tx(bars + 8 * B_W, 8192); bulk_load(sb + OFF_D, dtab, 8192, bars + 8 * B_W); }
      asm volatile("barrier.cluster.wait.aligned;" ::: "memory");
      mbar_wait(bars + 8 * B_W, 0);
      mbar_wait(bars + 8 * B_HX, 0);
      if (t == 0) PROF_EV(12);
      const uint32_t dd = (sb & 0x3FFFF) >> 4;
      const uint64_t dF = d128((dd + (OFF_D >> 4)) | (512u << 16)), dI = d128((dd + (OFF_D >> 4)) | (1u << 16)), dA = d128((dd + (OFF_XB >> 4)) | (512u << 16));
      float az[32];
      const int zero = blockIdx.x >> 16;
      uint32_t pf[32];
#pragma unroll
      for (int mt = 0; mt < 2; mt++) {
        wg_fence();
        if (mt == 0) mma_ss64<0, 3, 0>(az, dA, dF);
        else mma_ss64<0, 3, 2>(az, dA + 512, dF, zero);
#pragma unroll
        for (int k = 1; k < 4; k++) mma_ss64<0, 3, 1>(az, dA + (mt * 512 + k * 128), dF + k * 128);
        wg_commit();
        wg_wait<0>();
        fence_regs<0, 32>(az);
#pragma unroll
        for (int i = 0; i < 16; i++) {
          const float wr = bf_lo(wf[16 * mt + i]), wi = bf_hi(wf[16 * mt + i]);
          pf[16 * mt + i] = pack_pin(fmaf(az[2 * i], wr, -az[2 * i + 1] * wi), fmaf(az[2 * i], wi, az[2 * i + 1] * wr));
        }
      }
      if (t == 0) PROF_EV(16);
      {
        const int m = lane >> 3, r = lane & 7;
        const int sl = 2 * (m >> 1) + ((r >> 1) & 1) + 4 * (r >> 2);
        const uint32_t a0 = sb + OFF_XB + (2 * w + (m & 1)) * 2048 + sl * 64;
        uint32_t pk[16];
#pragma unroll
        for (int mt = 0; mt < 3; mt++) {
          if (mt < 2) {
            wg_fence();
            mma_rs64<0, 0, 2>(az, pf[16 * mt], pf[16 * mt + 1], pf[16 * mt + 2], pf[16 * mt + 3], dI, mt ? (int)helper : zero);
#pragma unroll
            for (int k = 1; k < 4; k++) mma_rs64<0, 0, 1>(az, pf[16 * mt + 4 * k], pf[16 * mt + 4 * k + 1], pf[16 * mt + 4 * k + 2], pf[16 * mt + 4 * k + 3], dI + k * 2);
            wg_commit();
          }
          if (mt > 0 && !helper) {
#pragma unroll
            for (int i = 0; i < 4; i++) stsm4t(a0 + ((((mt - 1) * 2 + (r & 1)) ^ (sl >> 1)) << 4) + i * 512, pk[4 * i], pk[4 * i + 1], pk[4 * i + 2], pk[4 * i + 3]);
          }
          if (mt < 2) {
            wg_wait<0>();
            fence_regs<0, 32>(az);
#pragma unroll
            for (int i = 0; i < 16; i++) pk[i] = pack_pin(az[2 * i], az[2 * i + 1]);
          }
        }
      }
      if (helper) {
#pragma unroll
        for (int i = 0; i < 16; i++) {
          const int n = i >> 1, s0 = 8 * (n >> 1) + 2 * (n & 1) + (q & 1) + 4 * (q >> 1);
          if ((n & 1) == (int)(blockIdx.x & 1)) st_u2(ws->Ts + s0 * 64 + 16 * w + g + 8 * (i & 1), pack_bf16(az[2 * i], az[2 * i + 1]), tag);
        }
        __syncwarp();
        hint_add_if(lane == 0, &ws->cntH[0]);
        if (t == 0) { ws->epoch[blockIdx.x * 8] = ep + 1; PROF_EV(13); }
      } else {
        asm volatile("fence.proxy.async.shared::cta;" ::: "memory");
        __syncwarp();
        if (elect_one()) {
          if (t == 0) PROF_EV(17);
          if (SPACE) __nanosleep(SPACE * w);
          asm volatile("cp.async.bulk.tensor.3d.global.shared::cta.bulk_group [%0, {%2, %3, %4}], [%1];" ::"l"(&maps.ts), "r"(sb + OFF_XB + w * 4096),
                       "r"(32 * kg), "r"(0), "r"(8 * tn + 2 * w) : "memory");
          bulk_done_signal(&ws->cntT[32 * j]);
          asm volatile("mbarrier.arrive.shared::cluster.b64 _, [%0];" ::"r"(mapa(bars + 8 * B_RD0, rank ^ 1)) : "memory");
          if (t == 96) PROF_EV(13);
        }
        __syncwarp();
        if (j == 0) {
          hint_wait(&ws->cntH[0], (ep + 1) * 8u);
          const uint32_t t0 = (uint32_t)clock();
          float2 v;
          do { v = ld_x2((const float2*)ws->Ts + 2 * rb * 64 + t); spin_guard(t0); } while (__any_sync(0xffffffffu, (__float_as_uint(v.y) ^ tag) & 1));
          mbar_wait(bars + 8 * B_TL, 0);
          const uint32_t u = __float_as_uint(v.x);
          *(uint16_t*)(smem + OFF_T + t * 128 + ((t & 7) << 4)) = (uint16_t)u;
          *(uint16_t*)(smem + OFF_T + t * 128 + (((t & 7) ^ 1) << 4)) = (uint16_t)(u >> 16);
          asm volatile("fence.proxy.async.shared::cta;" ::: "memory");
          __syncwarp();
          mbar_arrive_if(lane == 0, bars + 8 * B_T);
        }
      }
    }
  } else {
    asm volatile("setmaxnreg.dec.sync.aligned.u32 24;");
    auto xf_load = [&](int q) {
      const uint32_t fb = bars + 8 * (B_FX + q);
      mbar_expect_tx(fb, U + 8192);
      tma3d(sb + q * U, &maps.x, fb, 64 * q, 0, 2 * rb);
      if (q >= 4) mbar_wait(bars + 8 * (B_FE + ((q - 4) >> 1)), 0);
      tma2d(sb + OFF_XB + (q & 3) * 8192, &maps.ft, fb, 64 * q, 64 * j);
    };
    if (elect_one()) {
      if (warp == 14) {
#pragma unroll
        for (int i = 0; i < B_FT; i++) mbar_init(bars + 8 * i, 1);
        asm volatile("fence.mbarrier_init.release.cluster;" ::: "memory");
        if (!helper) {
#pragma unroll 1
          for (int n = 0; n < 2; n++) {
            const uint32_t fb = bars + 8 * (B_FA + n);
            xf_load(2 * n); xf_load(2 * n + 1);
            mbar_expect_tx(fb, U);
            tma2d(sb + OFF_RING + n * U, &maps.g64, fb, f_full, 64 * n);
            tma2d(sb + OFF_RING + n * U + 8192, &maps.u64, fb, f_full, 64 * n);
          }
        }
      } else if (warp == 15) {
#pragma unroll
        for (int i = B_FT; i < NBAR; i++) mbar_init(bars + 8 * i, i < B_EA ? 1 : i < B_T ? 2 : 4);
#pragma unroll
        for (int i = 0; i < 8; i++) mbar_expect_tx(bars + 8 * (B_Z + i), U / 2);
        asm volatile("fence.mbarrier_init.release.cluster;" ::: "memory");
        asm volatile("fence.proxy.async.shared::cta;" ::: "memory");
      }
    }
    __syncwarp();
    asm volatile("bar.arrive 0, 384;" ::: "memory");
    asm volatile("bar.arrive 4, 256;" ::: "memory");
    __syncwarp();
    asm volatile("barrier.cluster.arrive.relaxed.aligned;" ::: "memory");
    asm volatile("bar.sync 3, 128;" ::: "memory");
    if (warp == 15 && !helper) {
        mbar_wait(bars + 8 * B_FE, 0);
        const uint32_t tag = (ld_x1(&ws->epoch[blockIdx.x * 8]) + 1) & 1;
        const int c = lane >> 4, jj = 16 * blockIdx.x + (lane & 15), jm = (2048 - jj) & 2047;
        const unsigned short* pr = (const unsigned short*)w_r + 256 * c;
        const unsigned short* pi = (const unsigned short*)w_i + 256 * c;
        const float wr = 0.25f * (bf_lo(__ldg(pr + jj * 257)) + bf_lo(__ldg(pr + jm * 257)));
        const float wi = 0.25f * (bf_lo(__ldg(pi + jj * 257)) - bf_lo(__ldg(pi + jm * 257)));
        st_u2(ws->Wh + c * 2048 + jj, c ? pack_bf16(-wi, wr) : pack_bf16(wr, wi), tag);
        __syncwarp();
        hint_add_if(lane == 0, &ws->cntW[0]);
        mbar_wait(bars + 8 * B_XS, 0);
        const uint32_t t0 = (uint32_t)clock();
        uint4 v;
        do { v = ld_x4(ws->gate + rb * 128 + 4 * lane); spin_guard(t0); } while (__any_sync(0xffffffffu, ((v.x ^ tag) | (v.y ^ tag) | (v.z ^ tag) | (v.w ^ tag)) & 1));
        *(uint4*)(smem + OFF_G + lane * 16) = v;
        __syncwarp();
        mbar_arrive_if(lane < 4, bars + 8 * B_G);
      }
    auto part_load = [&](int i, unsigned ep1) {
      flag_wait(&ws->cntP[32 * (rb * 8 + j) + 8 * i], ep1 * 8u);
      mbar_wait(bars + 8 * (B_PZ + (i == 0)), 0);
      if (i == 2) PROF_EV(26);
      mbar_expect_tx(bars + 8 * (B_HP + i), U);
      bulk_load(sb + (i ? (i - 1) * U : OFF_T), ws->part + (size_t)((rb * 8 + j) * 3 + i) * 1024, U, bars + 8 * (B_HP + i));
    };
    if ((!helper || warp == 15) && elect_one()) {
      if (warp < 14) {
        const int p = warp - 12;
#pragma unroll 1
        for (int i = 4 + p; i < 13; i += 2) asm volatile("prefetch.tensormap [%0];" ::"l"((const char*)&maps + i * 128) : "memory");
#pragma unroll 1
        for (int n = 2; n < 31; n++) {
          const bool table = n == 4 || n >= 29;
          const bool half = n >= 17 && n < 21;
          const int q = n < 4 ? n : n < 17 ? n - 1 : n - 5;
          const CUtensorMap* m = table ? &maps.e : half ? &maps.g32 + p : &maps.g64 + p;
          const int c0 = table ? 0 : half ? f_half : f_full + 64 * (q >> 3);
          const int c1 = table ? (2 * rb + ((n & 1) ^ 1)) * 128 + 64 * p : half ? 128 * (n - 17) : 64 * (q & 7);
          const uint32_t fb = bars + 8 * (B_FA + (n & 3)), dst = sb + OFF_RING + (n & 3) * U + p * 8192;
          if (n < 4) mbar_wait(bars + 8 * (B_FE + n - 2), 0);
          else mbar_wait(bars + 8 * (B_EA + (n & 3)), ((n >> 2) & 1) ^ 1);
          tma2d(dst, m, fb, c0, c1);
          if (p == 0) mbar_expect_tx(fb, U);
        }
        mbar_wait(bars + 8 * (B_PZ + 1), 0);
        part_load(1 + p, ld_x1(&ws->epoch[blockIdx.x * 8]) + 1);
      } else if (warp == 15) {
        const unsigned ep1 = ld_x1(&ws->epoch[blockIdx.x * 8]) + 1;
        flag_wait(&ws->cntX[helper ? 0 : 32 * j], ep1 * 16u);
        PROF_EV(22);
        mbar_expect_tx(bars + 8 * B_HX, U);
        bulk_load(sb + OFF_XB, ws->X + (size_t)(helper ? 128 : kg * 8 + tn) * 8192, U, bars + 8 * B_HX);
        if (!helper) {
          flag_wait(&ws->cntT[32 * j], ep1 * 64u);
          PROF_EV(23);
          mbar_expect_tx(bars + 8 * B_TL, U);
          tma3d(sb + OFF_T, &maps.t, bars + 8 * B_TL, 64 * j, 0, 2 * rb);
          part_load(0, ep1);
          mbar_wait(bars + 8 * (B_HP + 1), 0); mbar_wait(bars + 8 * (B_HP + 2), 0);
          ws->epoch[blockIdx.x * 8] = ep1;
        }
      } else {
#pragma unroll 1
        for (int q = 4; q < 8; q++) xf_load(q);
        mbar_wait(bars + 8 * (B_FE + 2), 0);
        mbar_expect_tx(bars + 8 * B_E0, U);
        tma2d(sb + OFF_XB, &maps.e, bars + 8 * B_E0, 0, 2 * rb * 128);
        tma2d(sb + OFF_XB + 8192, &maps.e, bars + 8 * B_E0, 0, 2 * rb * 128 + 64);
#pragma unroll 1
        for (int h2 = 0; h2 < 2; h2++) {
          const int s0 = 2 * rb + h2, sg = (s0 & ~6) | ((s0 & 2) << 1) | ((s0 & 4) >> 1);
          mbar_wait(bars + 8 * (B_XS + h2), 0);
#pragma unroll 1
          for (int c = 0; c < 2; c++) {
            asm volatile("cp.async.bulk.tensor.4d.global.shared::cta.bulk_group [%0, {%2, %3, %4, %5}], [%1];" ::"l"(&maps.xs),
                         "r"(sb + OFF_XB + h2 * 8192 + c * 4096), "r"(0), "r"(sg), "r"(0), "r"(16 * j + 8 * c) : "memory");
            if (j == 0)
              asm volatile("cp.async.bulk.global.shared::cta.bulk_group [%0], [%1], 256;" ::"l"(ws->X + 128 * 8192 + c * 4096 + sg * 128),
                           "r"(sb + OFF_SP + h2 * 512 + c * 256) : "memory");
            if (SPACE && h2 + c < 2) __nanosleep(SPACE);
          }
        }
        bulk_done_signal(&ws->cntX[32 * j]);
        PROF_EV(20);
#pragma unroll 1
        for (int t = 0; t < 8; t++) {
          const int i = t < 3 ? t + 1 : t < 6 ? t - 2 : 0;
          const int col = 64 * (2 * ((q4 + i) & 3) + ((t < 3 || t == 6) ? 1 - rank : rank));
          const uint32_t fb = bars + 8 * (B_FT + (t & 3)), dst = sb + (t & 3) * TB;
          mbar_wait(bars + 8 * (B_ET + (t < 3 ? t + 1 : t & 3)), t >> 2);
          mbar_expect_tx(fb, TB);
          tma2d(dst, &maps.d224, fb, col, 224 * j);
          if (t < 2) mbar_wait(bars + 8 * (B_ET + t + 1), 0);
          tma2d(dst + 28672, &maps.ft, fb, col, 64 * j);
        }
      }
    }
  }
}

typedef CUresult (*EncodeFn)(CUtensorMap*, CUtensorMapDataType, cuuint32_t, void*, const cuuint64_t*, const cuuint64_t*, const cuuint32_t*,
                             const cuuint32_t*, CUtensorMapInterleave, CUtensorMapSwizzle, CUtensorMapL2promotion, CUtensorMapFloatOOBfill);

static void encode(EncodeFn f, CUtensorMap* m, const void* base, int rank, const cuuint64_t* dims, const cuuint64_t* strides, const cuuint32_t* box,
                   CUtensorMapSwizzle sw) {
  cuuint32_t es[5] = {1, 1, 1, 1, 1};
  f(m, CU_TENSOR_MAP_DATA_TYPE_BFLOAT16, rank, (void*)base, dims, strides, box, es, CU_TENSOR_MAP_INTERLEAVE_NONE, sw,
    CU_TENSOR_MAP_L2_PROMOTION_L2_128B, CU_TENSOR_MAP_FLOAT_OOB_FILL_NONE);
}

extern "C" void kernel_launch(void* const* d_in, const int* in_sizes, int n_in, void* d_out, int out_size) {
  (void)in_sizes; (void)n_in; (void)out_size;
  const __nv_bfloat16* x = (const __nv_bfloat16*)d_in[0];
  const __nv_bfloat16* w_r = (const __nv_bfloat16*)d_in[1];
  const __nv_bfloat16* w_i = (const __nv_bfloat16*)d_in[2];
  const __nv_bfloat16* Wg = (const __nv_bfloat16*)d_in[4];
  const __nv_bfloat16* Wu = (const __nv_bfloat16*)d_in[5];
  const __nv_bfloat16* Wd = (const __nv_bfloat16*)d_in[6];
  const __nv_bfloat16* gw = (const __nv_bfloat16*)d_in[7];

  void* fp = nullptr; cudaDriverEntryPointQueryResult qr;
  cudaGetDriverEntryPoint("cuTensorMapEncodeTiled", &fp, cudaEnableDefault, &qr);
  EncodeFn enc = (EncodeFn)fp;
  void *pFT, *pET, *pDT, *pW;
  cudaGetSymbolAddress(&pDT, g_DT); cudaGetSymbolAddress(&pW, g_work);
  void *pX = ((Work*)pW)->X, *pT = ((Work*)pW)->T;
  cudaGetSymbolAddress(&pFT, g_FT); cudaGetSymbolAddress(&pET, g_ET);

  Maps mp;
  const CUtensorMapSwizzle S128 = CU_TENSOR_MAP_SWIZZLE_128B, S64 = CU_TENSOR_MAP_SWIZZLE_64B;
  { cuuint64_t d[3] = {512, 64, 32}, s[2] = {32768, 1024}; cuuint32_t b[3] = {64, 64, 2}; encode(enc, &mp.x, x, 3, d, s, b, S128); }
  { cuuint64_t d[2] = {512, 512}, s[1] = {1024}; cuuint32_t b[2] = {64, 64}; encode(enc, &mp.ft, pFT, 2, d, s, b, S128); }
  { cuuint64_t d[4] = {128, 32, 2, 129}, s[3] = {256, 8192, 16384}; cuuint32_t b[4] = {128, 1, 2, 8}; encode(enc, &mp.xs, pX, 4, d, s, b, CU_TENSOR_MAP_SWIZZLE_NONE); }
  { cuuint64_t d[3] = {512, 32, 64}, s[2] = {65536, 1024}; cuuint32_t b[3] = {32, 32, 2}; encode(enc, &mp.ts, pT, 3, d, s, b, S64); }
  { cuuint64_t d[3] = {512, 64, 32}, s[2] = {1024, 65536}; cuuint32_t b[3] = {64, 64, 2}; encode(enc, &mp.t, pT, 3, d, s, b, S128); }
  { cuuint64_t d[2] = {64, 4096}, s[1] = {128}; cuuint32_t b[2] = {64, 64}; encode(enc, &mp.e, pET, 2, d, s, b, S128); }
  { cuuint64_t d[2] = {1792, 512}, s[1] = {3584}; cuuint32_t b[2] = {64, 64}, b2[2] = {32, 128};
    encode(enc, &mp.g64, Wg, 2, d, s, b, S128); encode(enc, &mp.u64, Wu, 2, d, s, b, S128);
    encode(enc, &mp.g32, Wg, 2, d, s, b2, S64); encode(enc, &mp.u32, Wu, 2, d, s, b2, S64); }
  { cuuint64_t d[2] = {512, 1792}, s[1] = {1024}; cuuint32_t b[2] = {64, 224}; encode(enc, &mp.d224, Wd, 2, d, s, b, S128); }
  { cuuint64_t d[4] = {264, 32, 8, 8}, s[3] = {32896, 512, 4112}; cuuint32_t b[4] = {24, 32, 2, 1};
    encode(enc, &mp.wr, w_r, 4, d, s, b, CU_TENSOR_MAP_SWIZZLE_NONE); encode(enc, &mp.wi, w_i, 4, d, s, b, CU_TENSOR_MAP_SWIZZLE_NONE); }

  cudaFuncSetAttribute(fused_kernel, cudaFuncAttributeMaxDynamicSharedMemorySize, SMEM_BYTES);
  fused_kernel<<<NCTA, 512, SMEM_BYTES>>>((Work*)pW, (const uint16_t*)pDT, w_r, w_i, gw, x, (__nv_bfloat16*)d_out, mp);
}
```

```cpp
#include <cuda_runtime.h>
#include <cuda_bf16.h>
#include <cuda.h>
#include <stdint.h>

namespace tbl {
constexpr double PI = 3.14159265358979323846264338327950288;
constexpr double sin_s(double x) { double t = x, s = x; for (int n = 1; n < 12; n++) { t *= -x * x / ((2 * n) * (2 * n + 1)); s += t; } return s; }
constexpr double cos_s(double x) { double t = 1, s = 1; for (int n = 1; n < 12; n++) { t *= -x * x / ((2 * n - 1) * (2 * n)); s += t; } return s; }
constexpr double cos2048(int m) {
  m &= 2047; if (m > 1024) m = 2048 - m;
  bool neg = false; if (m > 512) { m = 1024 - m; neg = true; }
  double v = (m <= 256) ? cos_s(2 * PI * m / 2048) : sin_s(2 * PI * (512 - m) / 2048);
  return neg ? -v : v;
}
constexpr uint16_t to_bf16(double v) {
  if (v == 0) return 0;
  uint16_t s = 0; if (v < 0) { s = 0x8000; v = -v; }
  int e = 0; while (v >= 2) { v /= 2; e++; } while (v < 1) { v *= 2; e--; }
  double m = (v - 1) * 128; int mi = (int)m; double fr = m - mi;
  if (fr > 0.5 || (fr == 0.5 && (mi & 1))) mi++;
  if (mi == 128) { mi = 0; e++; }
  return (uint16_t)(s | ((e + 127) << 7) | mi);
}
struct CosT { uint16_t v[2048]; constexpr CosT() : v() { for (int i = 0; i < 2048; i++) v[i] = to_bf16(cos2048(i)); } };
struct alignas(1024) FT {
  uint16_t v[512 * 512];
  constexpr FT() : v() {
    CosT c;
    for (int r = 0; r < 512; r++) {
      int k = (r >> 4) * 8 + (r & 7), e = (r >> 3) & 1;
      int mul = 4 * k, add = e ? 512 : 0;
      if (k == 0 && e == 1) { mul = 1024; add = 0; }
      for (int d = 0; d < 512; d++) v[r * 512 + d] = c.v[(d * mul + add) & 2047];
    }
  }
};
struct alignas(1024) ET {
  uint16_t v[2048 * 128];
  constexpr ET() : v() {
    CosT c;
    for (int s = 0; s < 2048; s++)
      for (int j = 0; j < 64; j++) {
        const int o = (s & 31) * 8192 + (s >> 5) * 64 + j;
        v[o] = c.v[(s * j) & 2047]; v[o + 4096] = c.v[(s * j + 512) & 2047];
      }
  }
};
struct alignas(1024) DT {
  uint16_t v[64 * 64];
  constexpr DT() : v() {
    CosT c;
    for (int r = 0; r < 64; r++)
      for (int n = 0; n < 64; n++) {
        const int sg = r >> 1, s0 = (sg & ~6) | ((sg & 2) << 1) | ((sg & 4) >> 1), e = r & 1, f = n & 1;
        const int m = 64 * s0 * (n >> 1) + (e == f ? 0 : e ? -512 : 512);
        v[r * 64 + (((n >> 3) ^ (r & 7)) << 3) + (n & 7)] = c.v[m & 2047];
      }
  }
};
}

__device__ constexpr tbl::FT g_FT = tbl::FT();
__device__ constexpr tbl::ET g_ET = tbl::ET();
__device__ constexpr tbl::DT g_DT = tbl::DT();

struct alignas(1024) Work {
  unsigned epoch[132 * 8];
  unsigned cntX[8 * 32], cntT[8 * 32], cntP[128 * 32], cntW[32], cntH[32];
  alignas(16) float gate[16 * 128];
  alignas(16) uint2 Wh[2 * 2048];
  alignas(16) uint2 Ts[32 * 64];
  alignas(1024) uint16_t X[129 * 8192];
  alignas(1024) uint16_t T[32 * 64 * 512];
  alignas(1024) uint4 part[128 * 3 * 1024];
};
__device__ Work g_work;
#define PROF_EV(i) do {} while (0)
#define PROF_CK(i) do {} while (0)

__device__ __forceinline__ uint32_t smem_u32(const void* p) { return (uint32_t)__cvta_generic_to_shared(p); }
__device__ __forceinline__ void mbar_init(uint32_t bar, uint32_t cnt) { asm volatile("mbarrier.init.shared::cta.b64 [%0], %1;" ::"r"(bar), "r"(cnt)); }
__device__ __forceinline__ void mbar_expect_tx(uint32_t bar, uint32_t bytes) { asm volatile("mbarrier.arrive.expect_tx.shared::cta.b64 _, [%0], %1;" ::"r"(bar), "r"(bytes) : "memory"); }
__device__ __forceinline__ void mbar_arrive(uint32_t bar) { asm volatile("mbarrier.arrive.shared::cta.b64 _, [%0];" ::"r"(bar) : "memory"); }
__device__ __forceinline__ bool elect_one() {
  uint32_t p;
  asm volatile("{\n.reg .pred p;\nelect.sync _|p, 0xffffffff;\nselp.u32 %0, 1, 0, p;\n}" : "=r"(p));
  return p;
}
__device__ __forceinline__ void mbar_arrive_if(bool p, uint32_t bar) {
  asm volatile("{\n.reg .pred p;\nsetp.ne.b32 p, %1, 0;\n@p mbarrier.arrive.shared::cta.b64 _, [%0];\n}" ::"r"(bar), "r"((int)p) : "memory");
}
__device__ __forceinline__ void hint_add_if(bool p, unsigned* a) {
  asm volatile("{\n.reg .pred p;\nsetp.ne.b32 p, %1, 0;\n@p red.relaxed.gpu.global.add.u32 [%0], 1;\n}" ::"l"(a), "r"((int)p) : "memory");
}
__device__ __forceinline__ bool mbar_try(uint32_t bar, uint32_t parity) {
  uint32_t ok;
  asm volatile("{\n.reg .pred p;\nmbarrier.test_wait.parity.shared::cta.b64 p, [%1], %2;\nselp.u32 %0, 1, 0, p;\n}" : "=r"(ok) : "r"(bar), "r"(parity) : "memory");
  return ok;
}
__device__ __forceinline__ void mbar_wait(uint32_t bar, uint32_t parity) {
  asm volatile(
      "{\n.reg .pred p;\n.reg .u32 n;\nmov.u32 n, 0;\n"
      "W_LOOP:\nmbarrier.try_wait.parity.shared::cta.b64 p, [%0], %1;\n@p bra W_DONE;\n"
      "add.u32 n, n, 1;\nsetp.lt.u32 p, n, 0x40000;\n@p bra W_LOOP;\ntrap;\nW_DONE:\n}" ::"r"(bar), "r"(parity) : "memory");
}
__device__ __forceinline__ void bulk_load(uint32_t dst, const void* src, uint32_t bytes, uint32_t bar) {
  asm volatile("cp.async.bulk.shared::cluster.global.mbarrier::complete_tx::bytes [%0], [%1], %2, [%3];" ::"r"(dst), "l"(src), "r"(bytes), "r"(bar) : "memory");
}
__device__ __forceinline__ void spin_guard(uint32_t t0) { if ((uint32_t)clock() - t0 > (1u << 30)) __trap(); }
__device__ __forceinline__ float2 ld_x2(const float2* p) { float2 v; asm volatile("ld.relaxed.gpu.global.v2.f32 {%0,%1}, [%2];" : "=f"(v.x), "=f"(v.y) : "l"(p) : "memory"); return v; }
__device__ __forceinline__ void st_u2(uint2* p, uint32_t a, uint32_t b) { asm volatile("st.relaxed.gpu.global.v2.u32 [%0], {%1,%2};" ::"l"(p), "r"(a), "r"(b) : "memory"); }
__device__ __forceinline__ uint32_t ld_x1(const void* p) { uint32_t v; asm volatile("ld.relaxed.gpu.global.u32 %0, [%1];" : "=r"(v) : "l"(p) : "memory"); return v; }
__device__ __forceinline__ uint4 ld_x4(const void* p) { uint4 v; asm volatile("ld.relaxed.gpu.global.v4.u32 {%0,%1,%2,%3}, [%4];" : "=r"(v.x), "=r"(v.y), "=r"(v.z), "=r"(v.w) : "l"(p) : "memory"); return v; }
__device__ __forceinline__ uint32_t mapa(uint32_t a, uint32_t cta) { uint32_t r; asm volatile("mapa.shared::cluster.u32 %0, %1, %2;" : "=r"(r) : "r"(a), "r"(cta)); return r; }
__device__ __forceinline__ void stsm4t(uint32_t a, uint32_t r0, uint32_t r1, uint32_t r2, uint32_t r3) {
  asm volatile("stmatrix.sync.aligned.m8n8.x4.trans.shared.b16 [%0], {%1,%2,%3,%4};" ::"r"(a), "r"(r0), "r"(r1), "r"(r2), "r"(r3) : "memory");
}
__device__ __forceinline__ void hint_add(unsigned* p) { asm volatile("red.relaxed.gpu.global.add.u32 [%0], 1;" ::"l"(p) : "memory"); }
__device__ __forceinline__ void hint_wait(const unsigned* p, unsigned target) {
  const uint32_t t0 = (uint32_t)clock();
  while ((int)(ld_x1(p) - target) < 0) spin_guard(t0);
}
__device__ __forceinline__ void bulk_done_signal(unsigned* p) {
  asm volatile("cp.async.bulk.commit_group;\ncp.async.bulk.wait_group 0;\nfence.proxy.async.global;" ::: "memory");
  hint_add(p);
}
__device__ __forceinline__ void flag_wait(const unsigned* p, unsigned target) {
  hint_wait(p, target);
  asm volatile("fence.proxy.async.global;" ::: "memory");
}
__device__ __forceinline__ void tma2d(uint32_t dst, const CUtensorMap* m, uint32_t bar, int c0, int c1) {
  asm volatile("cp.async.bulk.tensor.2d.shared::cluster.global.mbarrier::complete_tx::bytes [%0], [%1, {%3, %4}], [%2];" ::"r"(dst), "l"(m), "r"(bar), "r"(c0), "r"(c1) : "memory");
}
__device__ __forceinline__ void tma3d(uint32_t dst, const CUtensorMap* m, uint32_t bar, int c0, int c1, int c2) {
  asm volatile("cp.async.bulk.tensor.3d.shared::cluster.global.mbarrier::complete_tx::bytes [%0], [%1, {%3, %4, %5}], [%2];" ::"r"(dst), "l"(m), "r"(bar), "r"(c0), "r"(c1), "r"(c2) : "memory");
}
__device__ __forceinline__ void tma4d(uint32_t dst, const CUtensorMap* m, uint32_t bar, int c0, int c1, int c2, int c3) {
  asm volatile("cp.async.bulk.tensor.4d.shared::cluster.global.mbarrier::complete_tx::bytes [%0], [%1, {%3, %4, %5, %6}], [%2];" ::"r"(dst), "l"(m), "r"(bar), "r"(c0), "r"(c1), "r"(c2), "r"(c3) : "memory");
}
__device__ __forceinline__ void wg_fence() { asm volatile("wgmma.fence.sync.aligned;" ::: "memory"); }
__device__ __forceinline__ void wg_commit() { asm volatile("wgmma.commit_group.sync.aligned;" ::: "memory"); }
template <int N> __device__ __forceinline__ void wg_wait() { asm volatile("wgmma.wait_group.sync.aligned %0;" ::"n"(N) : "memory"); }
template <int O, int N, int NN> __device__ __forceinline__ void fence_regs(float (&d)[NN]) {
#pragma unroll
  for (int i = 0; i < N; i++) asm volatile("" : "+f"(d[O + i])::"memory");
}
__device__ __forceinline__ uint32_t pack_bf16(float lo, float hi) {
  uint32_t r; asm("cvt.rn.bf16x2.f32 %0, %1, %2;" : "=r"(r) : "f"(hi), "f"(lo)); return r;
}
__device__ __forceinline__ uint32_t pack_pin(float lo, float hi) {
  uint32_t r; asm volatile("cvt.rn.bf16x2.f32 %0, %1, %2;" : "=r"(r) : "f"(hi), "f"(lo) : "memory"); return r;
}
__device__ __forceinline__ uint32_t add_bf2(uint32_t a, uint32_t b) { uint32_t r; asm("add.rn.bf16x2 %0, %1, %2;" : "=r"(r) : "r"(a), "r"(b)); return r; }
__device__ __forceinline__ float bf_lo(uint32_t u) { return __uint_as_float(u << 16); }
__device__ __forceinline__ float bf_hi(uint32_t u) { return __uint_as_float(u & 0xffff0000u); }

__device__ __forceinline__ uint64_t d128(uint32_t lo) { uint64_t d; asm("mov.b64 %0, {%1, 0x40000040};" : "=l"(d) : "r"(lo)); return d; }
__device__ __forceinline__ uint64_t d64(uint32_t lo) { uint64_t d; asm("mov.b64 %0, {%1, 0x80000020};" : "=l"(d) : "r"(lo)); return d; }
template<int O,int TB,int ACC,int NN> __device__ __forceinline__ void mma_ss64(float (&d)[NN], uint64_t da, uint64_t db, int sd = 0){
  if constexpr (ACC == 1) asm volatile("wgmma.mma_async.sync.aligned.m64n64k16.f32.bf16.bf16 {%0,%1,%2,%3,%4,%5,%6,%7,%8,%9,%10,%11,%12,%13,%14,%15,%16,%17,%18,%19,%20,%21,%22,%23,%24,%25,%26,%27,%28,%29,%30,%31}, %32, %33, 1, 1, 1, %35, %34;"
   : "+f"(d[O+0]), "+f"(d[O+1]), "+f"(d[O+2]), "+f"(d[O+3]), "+f"(d[O+4]), "+f"(d[O+5]), "+f"(d[O+6]), "+f"(d[O+7]), "+f"(d[O+8]), "+f"(d[O+9]), "+f"(d[O+10]), "+f"(d[O+11]), "+f"(d[O+12]), "+f"(d[O+13]), "+f"(d[O+14]), "+f"(d[O+15]), "+f"(d[O+16]), "+f"(d[O+17]), "+f"(d[O+18]), "+f"(d[O+19]), "+f"(d[O+20]), "+f"(d[O+21]), "+f"(d[O+22]), "+f"(d[O+23]), "+f"(d[O+24]), "+f"(d[O+25]), "+f"(d[O+26]), "+f"(d[O+27]), "+f"(d[O+28]), "+f"(d[O+29]), "+f"(d[O+30]), "+f"(d[O+31])
   : "l"(da), "l"(db), "n"(TB & 1), "n"(TB >> 1));
  else if constexpr (ACC == 0) asm volatile("wgmma.mma_async.sync.aligned.m64n64k16.f32.bf16.bf16 {%0,%1,%2,%3,%4,%5,%6,%7,%8,%9,%10,%11,%12,%13,%14,%15,%16,%17,%18,%19,%20,%21,%22,%23,%24,%25,%26,%27,%28,%29,%30,%31}, %32, %33, 0, 1, 1, %35, %34;"
   : "=f"(d[O+0]), "=f"(d[O+1]), "=f"(d[O+2]), "=f"(d[O+3]), "=f"(d[O+4]), "=f"(d[O+5]), "=f"(d[O+6]), "=f"(d[O+7]), "=f"(d[O+8]), "=f"(d[O+9]), "=f"(d[O+10]), "=f"(d[O+11]), "=f"(d[O+12]), "=f"(d[O+13]), "=f"(d[O+14]), "=f"(d[O+15]), "=f"(d[O+16]), "=f"(d[O+17]), "=f"(d[O+18]), "=f"(d[O+19]), "=f"(d[O+20]), "=f"(d[O+21]), "=f"(d[O+22]), "=f"(d[O+23]), "=f"(d[O+24]), "=f"(d[O+25]), "=f"(d[O+26]), "=f"(d[O+27]), "=f"(d[O+28]), "=f"(d[O+29]), "=f"(d[O+30]), "=f"(d[O+31])
   : "l"(da), "l"(db), "n"(TB & 1), "n"(TB >> 1));
  else asm volatile("{\n.reg .pred p;\nsetp.ne.b32 p, %36, 0;\nwgmma.mma_async.sync.aligned.m64n64k16.f32.bf16.bf16 {%0,%1,%2,%3,%4,%5,%6,%7,%8,%9,%10,%11,%12,%13,%14,%15,%16,%17,%18,%19,%20,%21,%22,%23,%24,%25,%26,%27,%28,%29,%30,%31}, %32, %33, p, 1, 1, %35, %34;\n}"
   : "+f"(d[O+0]), "+f"(d[O+1]), "+f"(d[O+2]), "+f"(d[O+3]), "+f"(d[O+4]), "+f"(d[O+5]), "+f"(d[O+6]), "+f"(d[O+7]), "+f"(d[O+8]), "+f"(d[O+9]), "+f"(d[O+10]), "+f"(d[O+11]), "+f"(d[O+12]), "+f"(d[O+13]), "+f"(d[O+14]), "+f"(d[O+15]), "+f"(d[O+16]), "+f"(d[O+17]), "+f"(d[O+18]), "+f"(d[O+19]), "+f"(d[O+20]), "+f"(d[O+21]), "+f"(d[O+22]), "+f"(d[O+23]), "+f"(d[O+24]), "+f"(d[O+25]), "+f"(d[O+26]), "+f"(d[O+27]), "+f"(d[O+28]), "+f"(d[O+29]), "+f"(d[O+30]), "+f"(d[O+31])
   : "l"(da), "l"(db), "n"(TB & 1), "n"(TB >> 1), "r"(sd));
}
template<int O,int TB,int ACC,int NN> __device__ __forceinline__ void mma_rs64(float (&d)[NN], uint32_t a0, uint32_t a1, uint32_t a2, uint32_t a3, uint64_t db, int sd = 0){
  if constexpr (ACC == 1) asm volatile("wgmma.mma_async.sync.aligned.m64n64k16.f32.bf16.bf16 {%0,%1,%2,%3,%4,%5,%6,%7,%8,%9,%10,%11,%12,%13,%14,%15,%16,%17,%18,%19,%20,%21,%22,%23,%24,%25,%26,%27,%28,%29,%30,%31}, {%32,%33,%34,%35}, %36, 1, 1, 1, %37;"
   : "+f"(d[O+0]), "+f"(d[O+1]), "+f"(d[O+2]), "+f"(d[O+3]), "+f"(d[O+4]), "+f"(d[O+5]), "+f"(d[O+6]), "+f"(d[O+7]), "+f"(d[O+8]), "+f"(d[O+9]), "+f"(d[O+10]), "+f"(d[O+11]), "+f"(d[O+12]), "+f"(d[O+13]), "+f"(d[O+14]), "+f"(d[O+15]), "+f"(d[O+16]), "+f"(d[O+17]), "+f"(d[O+18]), "+f"(d[O+19]), "+f"(d[O+20]), "+f"(d[O+21]), "+f"(d[O+22]), "+f"(d[O+23]), "+f"(d[O+24]), "+f"(d[O+25]), "+f"(d[O+26]), "+f"(d[O+27]), "+f"(d[O+28]), "+f"(d[O+29]), "+f"(d[O+30]), "+f"(d[O+31])
   : "r"(a0), "r"(a1), "r"(a2), "r"(a3), "l"(db), "n"(TB));
  else if constexpr (ACC == 0) asm volatile("wgmma.mma_async.sync.aligned.m64n64k16.f32.bf16.bf16 {%0,%1,%2,%3,%4,%5,%6,%7,%8,%9,%10,%11,%12,%13,%14,%15,%16,%17,%18,%19,%20,%21,%22,%23,%24,%25,%26,%27,%28,%29,%30,%31}, {%32,%33,%34,%35}, %36, 0, 1, 1, %37;"
   : "=f"(d[O+0]), "=f"(d[O+1]), "=f"(d[O+2]), "=f"(d[O+3]), "=f"(d[O+4]), "=f"(d[O+5]), "=f"(d[O+6]), "=f"(d[O+7]), "=f"(d[O+8]), "=f"(d[O+9]), "=f"(d[O+10]), "=f"(d[O+11]), "=f"(d[O+12]), "=f"(d[O+13]), "=f"(d[O+14]), "=f"(d[O+15]), "=f"(d[O+16]), "=f"(d[O+17]), "=f"(d[O+18]), "=f"(d[O+19]), "=f"(d[O+20]), "=f"(d[O+21]), "=f"(d[O+22]), "=f"(d[O+23]), "=f"(d[O+24]), "=f"(d[O+25]), "=f"(d[O+26]), "=f"(d[O+27]), "=f"(d[O+28]), "=f"(d[O+29]), "=f"(d[O+30]), "=f"(d[O+31])
   : "r"(a0), "r"(a1), "r"(a2), "r"(a3), "l"(db), "n"(TB));
  else asm volatile("{\n.reg .pred p;\nsetp.ne.b32 p, %38, 0;\nwgmma.mma_async.sync.aligned.m64n64k16.f32.bf16.bf16 {%0,%1,%2,%3,%4,%5,%6,%7,%8,%9,%10,%11,%12,%13,%14,%15,%16,%17,%18,%19,%20,%21,%22,%23,%24,%25,%26,%27,%28,%29,%30,%31}, {%32,%33,%34,%35}, %36, p, 1, 1, %37;\n}"
   : "+f"(d[O+0]), "+f"(d[O+1]), "+f"(d[O+2]), "+f"(d[O+3]), "+f"(d[O+4]), "+f"(d[O+5]), "+f"(d[O+6]), "+f"(d[O+7]), "+f"(d[O+8]), "+f"(d[O+9]), "+f"(d[O+10]), "+f"(d[O+11]), "+f"(d[O+12]), "+f"(d[O+13]), "+f"(d[O+14]), "+f"(d[O+15]), "+f"(d[O+16]), "+f"(d[O+17]), "+f"(d[O+18]), "+f"(d[O+19]), "+f"(d[O+20]), "+f"(d[O+21]), "+f"(d[O+22]), "+f"(d[O+23]), "+f"(d[O+24]), "+f"(d[O+25]), "+f"(d[O+26]), "+f"(d[O+27]), "+f"(d[O+28]), "+f"(d[O+29]), "+f"(d[O+30]), "+f"(d[O+31])
   : "r"(a0), "r"(a1), "r"(a2), "r"(a3), "l"(db), "n"(TB), "r"(sd));
}
template<int O,int TB,int ACC,int NN> __device__ __forceinline__ void mma_ss128(float (&d)[NN], uint64_t da, uint64_t db, int sd = 0){
  if constexpr (ACC == 1) asm volatile("wgmma.mma_async.sync.aligned.m64n128k16.f32.bf16.bf16 {%0,%1,%2,%3,%4,%5,%6,%7,%8,%9,%10,%11,%12,%13,%14,%15,%16,%17,%18,%19,%20,%21,%22,%23,%24,%25,%26,%27,%28,%29,%30,%31,%32,%33,%34,%35,%36,%37,%38,%39,%40,%41,%42,%43,%44,%45,%46,%47,%48,%49,%50,%51,%52,%53,%54,%55,%56,%57,%58,%59,%60,%61,%62,%63}, %64, %65, 1, 1, 1, %67, %66;"
   : "+f"(d[O+0]), "+f"(d[O+1]), "+f"(d[O+2]), "+f"(d[O+3]), "+f"(d[O+4]), "+f"(d[O+5]), "+f"(d[O+6]), "+f"(d[O+7]), "+f"(d[O+8]), "+f"(d[O+9]), "+f"(d[O+10]), "+f"(d[O+11]), "+f"(d[O+12]), "+f"(d[O+13]), "+f"(d[O+14]), "+f"(d[O+15]), "+f"(d[O+16]), "+f"(d[O+17]), "+f"(d[O+18]), "+f"(d[O+19]), "+f"(d[O+20]), "+f"(d[O+21]), "+f"(d[O+22]), "+f"(d[O+23]), "+f"(d[O+24]), "+f"(d[O+25]), "+f"(d[O+26]), "+f"(d[O+27]), "+f"(d[O+28]), "+f"(d[O+29]), "+f"(d[O+30]), "+f"(d[O+31]), "+f"(d[O+32]), "+f"(d[O+33]), "+f"(d[O+34]), "+f"(d[O+35]), "+f"(d[O+36]), "+f"(d[O+37]), "+f"(d[O+38]), "+f"(d[O+39]), "+f"(d[O+40]), "+f"(d[O+41]), "+f"(d[O+42]), "+f"(d[O+43]), "+f"(d[O+44]), "+f"(d[O+45]), "+f"(d[O+46]), "+f"(d[O+47]), "+f"(d[O+48]), "+f"(d[O+49]), "+f"(d[O+50]), "+f"(d[O+51]), "+f"(d[O+52]), "+f"(d[O+53]), "+f"(d[O+54]), "+f"(d[O+55]), "+f"(d[O+56]), "+f"(d[O+57]), "+f"(d[O+58]), "+f"(d[O+59]), "+f"(d[O+60]), "+f"(d[O+61]), "+f"(d[O+62]), "+f"(d[O+63])
   : "l"(da), "l"(db), "n"(TB & 1), "n"(TB >> 1));
  else if constexpr (ACC == 0) asm volatile("wgmma.mma_async.sync.aligned.m64n128k16.f32.bf16.bf16 {%0,%1,%2,%3,%4,%5,%6,%7,%8,%9,%10,%11,%12,%13,%14,%15,%16,%17,%18,%19,%20,%21,%22,%23,%24,%25,%26,%27,%28,%29,%30,%31,%32,%33,%34,%35,%36,%37,%38,%39,%40,%41,%42,%43,%44,%45,%46,%47,%48,%49,%50,%51,%52,%53,%54,%55,%56,%57,%58,%59,%60,%61,%62,%63}, %64, %65, 0, 1, 1, %67, %66;"
   : "=f"(d[O+0]), "=f"(d[O+1]), "=f"(d[O+2]), "=f"(d[O+3]), "=f"(d[O+4]), "=f"(d[O+5]), "=f"(d[O+6]), "=f"(d[O+7]), "=f"(d[O+8]), "=f"(d[O+9]), "=f"(d[O+10]), "=f"(d[O+11]), "=f"(d[O+12]), "=f"(d[O+13]), "=f"(d[O+14]), "=f"(d[O+15]), "=f"(d[O+16]), "=f"(d[O+17]), "=f"(d[O+18]), "=f"(d[O+19]), "=f"(d[O+20]), "=f"(d[O+21]), "=f"(d[O+22]), "=f"(d[O+23]), "=f"(d[O+24]), "=f"(d[O+25]), "=f"(d[O+26]), "=f"(d[O+27]), "=f"(d[O+28]), "=f"(d[O+29]), "=f"(d[O+30]), "=f"(d[O+31]), "=f"(d[O+32]), "=f"(d[O+33]), "=f"(d[O+34]), "=f"(d[O+35]), "=f"(d[O+36]), "=f"(d[O+37]), "=f"(d[O+38]), "=f"(d[O+39]), "=f"(d[O+40]), "=f"(d[O+41]), "=f"(d[O+42]), "=f"(d[O+43]), "=f"(d[O+44]), "=f"(d[O+45]), "=f"(d[O+46]), "=f"(d[O+47]), "=f"(d[O+48]), "=f"(d[O+49]), "=f"(d[O+50]), "=f"(d[O+51]), "=f"(d[O+52]), "=f"(d[O+53]), "=f"(d[O+54]), "=f"(d[O+55]), "=f"(d[O+56]), "=f"(d[O+57]), "=f"(d[O+58]), "=f"(d[O+59]), "=f"(d[O+60]), "=f"(d[O+61]), "=f"(d[O+62]), "=f"(d[O+63])
   : "l"(da), "l"(db), "n"(TB & 1), "n"(TB >> 1));
  else asm volatile("{\n.reg .pred p;\nsetp.ne.b32 p, %68, 0;\nwgmma.mma_async.sync.aligned.m64n128k16.f32.bf16.bf16 {%0,%1,%2,%3,%4,%5,%6,%7,%8,%9,%10,%11,%12,%13,%14,%15,%16,%17,%18,%19,%20,%21,%22,%23,%24,%25,%26,%27,%28,%29,%30,%31,%32,%33,%34,%35,%36,%37,%38,%39,%40,%41,%42,%43,%44,%45,%46,%47,%48,%49,%50,%51,%52,%53,%54,%55,%56,%57,%58,%59,%60,%61,%62,%63}, %64, %65, p, 1, 1, %67, %66;\n}"
   : "+f"(d[O+0]), "+f"(d[O+1]), "+f"(d[O+2]), "+f"(d[O+3]), "+f"(d[O+4]), "+f"(d[O+5]), "+f"(d[O+6]), "+f"(d[O+7]), "+f"(d[O+8]), "+f"(d[O+9]), "+f"(d[O+10]), "+f"(d[O+11]), "+f"(d[O+12]), "+f"(d[O+13]), "+f"(d[O+14]), "+f"(d[O+15]), "+f"(d[O+16]), "+f"(d[O+17]), "+f"(d[O+18]), "+f"(d[O+19]), "+f"(d[O+20]), "+f"(d[O+21]), "+f"(d[O+22]), "+f"(d[O+23]), "+f"(d[O+24]), "+f"(d[O+25]), "+f"(d[O+26]), "+f"(d[O+27]), "+f"(d[O+28]), "+f"(d[O+29]), "+f"(d[O+30]), "+f"(d[O+31]), "+f"(d[O+32]), "+f"(d[O+33]), "+f"(d[O+34]), "+f"(d[O+35]), "+f"(d[O+36]), "+f"(d[O+37]), "+f"(d[O+38]), "+f"(d[O+39]), "+f"(d[O+40]), "+f"(d[O+41]), "+f"(d[O+42]), "+f"(d[O+43]), "+f"(d[O+44]), "+f"(d[O+45]), "+f"(d[O+46]), "+f"(d[O+47]), "+f"(d[O+48]), "+f"(d[O+49]), "+f"(d[O+50]), "+f"(d[O+51]), "+f"(d[O+52]), "+f"(d[O+53]), "+f"(d[O+54]), "+f"(d[O+55]), "+f"(d[O+56]), "+f"(d[O+57]), "+f"(d[O+58]), "+f"(d[O+59]), "+f"(d[O+60]), "+f"(d[O+61]), "+f"(d[O+62]), "+f"(d[O+63])
   : "l"(da), "l"(db), "n"(TB & 1), "n"(TB >> 1), "r"(sd));
}
template<int O,int TB,int ACC,int NN> __device__ __forceinline__ void mma_rs128(float (&d)[NN], uint32_t a0, uint32_t a1, uint32_t a2, uint32_t a3, uint64_t db, int sd = 0){
  if constexpr (ACC == 1) asm volatile("wgmma.mma_async.sync.aligned.m64n128k16.f32.bf16.bf16 {%0,%1,%2,%3,%4,%5,%6,%7,%8,%9,%10,%11,%12,%13,%14,%15,%16,%17,%18,%19,%20,%21,%22,%23,%24,%25,%26,%27,%28,%29,%30,%31,%32,%33,%34,%35,%36,%37,%38,%39,%40,%41,%42,%43,%44,%45,%46,%47,%48,%49,%50,%51,%52,%53,%54,%55,%56,%57,%58,%59,%60,%61,%62,%63}, {%64,%65,%66,%67}, %68, 1, 1, 1, %69;"
   : "+f"(d[O+0]), "+f"(d[O+1]), "+f"(d[O+2]), "+f"(d[O+3]), "+f"(d[O+4]), "+f"(d[O+5]), "+f"(d[O+6]), "+f"(d[O+7]), "+f"(d[O+8]), "+f"(d[O+9]), "+f"(d[O+10]), "+f"(d[O+11]), "+f"(d[O+12]), "+f"(d[O+13]), "+f"(d[O+14]), "+f"(d[O+15]), "+f"(d[O+16]), "+f"(d[O+17]), "+f"(d[O+18]), "+f"(d[O+19]), "+f"(d[O+20]), "+f"(d[O+21]), "+f"(d[O+22]), "+f"(d[O+23]), "+f"(d[O+24]), "+f"(d[O+25]), "+f"(d[O+26]), "+f"(d[O+27]), "+f"(d[O+28]), "+f"(d[O+29]), "+f"(d[O+30]), "+f"(d[O+31]), "+f"(d[O+32]), "+f"(d[O+33]), "+f"(d[O+34]), "+f"(d[O+35]), "+f"(d[O+36]), "+f"(d[O+37]), "+f"(d[O+38]), "+f"(d[O+39]), "+f"(d[O+40]), "+f"(d[O+41]), "+f"(d[O+42]), "+f"(d[O+43]), "+f"(d[O+44]), "+f"(d[O+45]), "+f"(d[O+46]), "+f"(d[O+47]), "+f"(d[O+48]), "+f"(d[O+49]), "+f"(d[O+50]), "+f"(d[O+51]), "+f"(d[O+52]), "+f"(d[O+53]), "+f"(d[O+54]), "+f"(d[O+55]), "+f"(d[O+56]), "+f"(d[O+57]), "+f"(d[O+58]), "+f"(d[O+59]), "+f"(d[O+60]), "+f"(d[O+61]), "+f"(d[O+62]), "+f"(d[O+63])
   : "r"(a0), "r"(a1), "r"(a2), "r"(a3), "l"(db), "n"(TB));
  else if constexpr (ACC == 0) asm volatile("wgmma.mma_async.sync.aligned.m64n128k16.f32.bf16.bf16 {%0,%1,%2,%3,%4,%5,%6,%7,%8,%9,%10,%11,%12,%13,%14,%15,%16,%17,%18,%19,%20,%21,%22,%23,%24,%25,%26,%27,%28,%29,%30,%31,%32,%33,%34,%35,%36,%37,%38,%39,%40,%41,%42,%43,%44,%45,%46,%47,%48,%49,%50,%51,%52,%53,%54,%55,%56,%57,%58,%59,%60,%61,%62,%63}, {%64,%65,%66,%67}, %68, 0, 1, 1, %69;"
   : "=f"(d[O+0]), "=f"(d[O+1]), "=f"(d[O+2]), "=f"(d[O+3]), "=f"(d[O+4]), "=f"(d[O+5]), "=f"(d[O+6]), "=f"(d[O+7]), "=f"(d[O+8]), "=f"(d[O+9]), "=f"(d[O+10]), "=f"(d[O+11]), "=f"(d[O+12]), "=f"(d[O+13]), "=f"(d[O+14]), "=f"(d[O+15]), "=f"(d[O+16]), "=f"(d[O+17]), "=f"(d[O+18]), "=f"(d[O+19]), "=f"(d[O+20]), "=f"(d[O+21]), "=f"(d[O+22]), "=f"(d[O+23]), "=f"(d[O+24]), "=f"(d[O+25]), "=f"(d[O+26]), "=f"(d[O+27]), "=f"(d[O+28]), "=f"(d[O+29]), "=f"(d[O+30]), "=f"(d[O+31]), "=f"(d[O+32]), "=f"(d[O+33]), "=f"(d[O+34]), "=f"(d[O+35]), "=f"(d[O+36]), "=f"(d[O+37]), "=f"(d[O+38]), "=f"(d[O+39]), "=f"(d[O+40]), "=f"(d[O+41]), "=f"(d[O+42]), "=f"(d[O+43]), "=f"(d[O+44]), "=f"(d[O+45]), "=f"(d[O+46]), "=f"(d[O+47]), "=f"(d[O+48]), "=f"(d[O+49]), "=f"(d[O+50]), "=f"(d[O+51]), "=f"(d[O+52]), "=f"(d[O+53]), "=f"(d[O+54]), "=f"(d[O+55]), "=f"(d[O+56]), "=f"(d[O+57]), "=f"(d[O+58]), "=f"(d[O+59]), "=f"(d[O+60]), "=f"(d[O+61]), "=f"(d[O+62]), "=f"(d[O+63])
   : "r"(a0), "r"(a1), "r"(a2), "r"(a3), "l"(db), "n"(TB));
  else asm volatile("{\n.reg .pred p;\nsetp.ne.b32 p, %70, 0;\nwgmma.mma_async.sync.aligned.m64n128k16.f32.bf16.bf16 {%0,%1,%2,%3,%4,%5,%6,%7,%8,%9,%10,%11,%12,%13,%14,%15,%16,%17,%18,%19,%20,%21,%22,%23,%24,%25,%26,%27,%28,%29,%30,%31,%32,%33,%34,%35,%36,%37,%38,%39,%40,%41,%42,%43,%44,%45,%46,%47,%48,%49,%50,%51,%52,%53,%54,%55,%56,%57,%58,%59,%60,%61,%62,%63}, {%64,%65,%66,%67}, %68, p, 1, 1, %69;\n}"
   : "+f"(d[O+0]), "+f"(d[O+1]), "+f"(d[O+2]), "+f"(d[O+3]), "+f"(d[O+4]), "+f"(d[O+5]), "+f"(d[O+6]), "+f"(d[O+7]), "+f"(d[O+8]), "+f"(d[O+9]), "+f"(d[O+10]), "+f"(d[O+11]), "+f"(d[O+12]), "+f"(d[O+13]), "+f"(d[O+14]), "+f"(d[O+15]), "+f"(d[O+16]), "+f"(d[O+17]), "+f"(d[O+18]), "+f"(d[O+19]), "+f"(d[O+20]), "+f"(d[O+21]), "+f"(d[O+22]), "+f"(d[O+23]), "+f"(d[O+24]), "+f"(d[O+25]), "+f"(d[O+26]), "+f"(d[O+27]), "+f"(d[O+28]), "+f"(d[O+29]), "+f"(d[O+30]), "+f"(d[O+31]), "+f"(d[O+32]), "+f"(d[O+33]), "+f"(d[O+34]), "+f"(d[O+35]), "+f"(d[O+36]), "+f"(d[O+37]), "+f"(d[O+38]), "+f"(d[O+39]), "+f"(d[O+40]), "+f"(d[O+41]), "+f"(d[O+42]), "+f"(d[O+43]), "+f"(d[O+44]), "+f"(d[O+45]), "+f"(d[O+46]), "+f"(d[O+47]), "+f"(d[O+48]), "+f"(d[O+49]), "+f"(d[O+50]), "+f"(d[O+51]), "+f"(d[O+52]), "+f"(d[O+53]), "+f"(d[O+54]), "+f"(d[O+55]), "+f"(d[O+56]), "+f"(d[O+57]), "+f"(d[O+58]), "+f"(d[O+59]), "+f"(d[O+60]), "+f"(d[O+61]), "+f"(d[O+62]), "+f"(d[O+63])
   : "r"(a0), "r"(a1), "r"(a2), "r"(a3), "l"(db), "n"(TB), "r"(sd));
}

#define NEARLY 0
#define XAHEAD 3
#define HEADN 6
#define WBATCH 1
#define WB 8
#define WSLEEP 20
#define XSPREAD 4
#define NOSEND 0
#define MSPLIT 2
#define PFALL 1
#define L2PF 0
#define STAG 0
#define EPF 2
#define XNB 2
#define FNB 0
#define GNB 0
#define TH 4
#define PF0 4
#define FSPLIT 1
#define MGLU 1
#define SPC 2
#define TL 14
#define GKB 4
#define T0A 8
#define TGATE 1
#define FIN32 1
#define SPACE 100
#define WPF 1
#define WAFTER 7
#define WPACE 0
#define GATE_AT 4
#define TPACE 40
#define PFMODE 0
#define MAPMODE 1
template <int V> struct IC { static constexpr int value = V; };
struct Maps { CUtensorMap x, ft, g64, u64, e, wr, wi, xs, ts, t, g32, u32, d224; };

constexpr int NCTA = 130;
constexpr int U = 16384;
constexpr int TB = 36864;
constexpr int OFF_RING = 8 * U, OFF_Z = 12 * U, OFF_XB = 12 * U, OFF_T = 13 * U, OFF_D = OFF_T;
constexpr int OFF_BAR = 14 * U, OFF_SP = OFF_BAR + 512, OFF_G = OFF_SP + 1024 + 128;
constexpr int SMEM_BYTES = OFF_G + 512;
constexpr int B_FX = 0, B_FA = 8, B_FT = 12, B_Z = 16, B_W = 24, B_HX = 25, B_TL = 26, B_HP = 27, B_WR = 31, B_E0 = 35;
constexpr int B_EA = 36, B_ET = 40, B_PZ = 44, B_RDY = 46, B_FE = 47;
constexpr int B_T = 51, B_XS = 52, B_G = 54, B_RD0 = 55, NBAR = 56;
__host__ __device__ constexpr int rslot(int n) { return n & 3; }
__host__ __device__ constexpr int rpar(int n) { return (n >> 2) & 1; }

__global__ void __cluster_dims__(2, 1, 1) __launch_bounds__(512, 1)
fused_kernel(Work* __restrict__ ws, const uint16_t* __restrict__ dtab, const __nv_bfloat16* __restrict__ w_r, const __nv_bfloat16* __restrict__ w_i,
             const __nv_bfloat16* __restrict__ gate_w, const __nv_bfloat16* __restrict__ x, __nv_bfloat16* __restrict__ out,
             const __grid_constant__ Maps maps) {
  extern __shared__ __align__(1024) uint8_t smem[];
  if (threadIdx.x < 32 && elect_one()) {
#pragma unroll
    for (int i = 0; i < PF0; i++) asm volatile("prefetch.tensormap [%0];" ::"l"((const char*)&maps + i * 128) : "memory");
  }
  const uint32_t sb = smem_u32(smem);
  const uint32_t bars = sb + OFF_BAR;
  const int tid = threadIdx.x, lane = tid & 31;
  const int warp = __shfl_sync(0xffffffffu, tid >> 5, 0);
  const bool helper = blockIdx.x >= 128;
  const int cl = (blockIdx.x >> 1) & 63, rank = blockIdx.x & 1;
  const int q4 = (cl & 1) | ((cl >> 2) & 2), rb = ((cl >> 1) & 3) | ((cl >> 4) << 2);
  const int j = 2 * q4 + rank;
  const int f_full = 448 * q4 + (rank ? 256 : 0);
  const int f_half = 448 * q4 + (rank ? 224 : 192);
  const int kg = 2 * j + (rb >> 3), tn = rb & 7;

  if (tid == 64) { PROF_EV(0); PROF_CK(40); }
  if (warp < 8) {
    if (!helper && tid < 32) {
      const int r = 16 * j + (tid & 15);
      asm volatile("prefetch.global.L2 [%0];" ::"l"(x + (size_t)(2 * rb + (r >> 6) + 32 * (r & 63)) * 512 + 64 * (tid >> 4)));
    }
    asm volatile("barrier.cluster.arrive.relaxed.aligned;" ::: "memory");
    asm volatile("setmaxnreg.inc.sync.aligned.u32 192;");
    if (!helper) {
      const int wg = warp >> 2, w = warp & 3, g = lane >> 2;
      const bool elect = (tid & 127) == 0;
      float cX[32], cA[64], cB[64], cC[64], ci[64], ct[64];
      const int zero = blockIdx.x >> 16;
      uint32_t h[56], yf[16];
      const uint32_t d0 = (sb & 0x3FFFF) >> 4;
      const uint32_t dK = d0 | (1u << 16), dN = d0 | (512u << 16);
      const uint32_t dX = dK + wg * 512;
      constexpr uint32_t RING = OFF_RING >> 4;
      auto waitA = [&](int n) { mbar_wait(bars + 8 * (B_FA + rslot(n)), rpar(n)); };
      auto freeA = [&](int n) { mbar_arrive_if(elect, bars + 8 * (B_EA + rslot(n))); };
      auto nop = [] {};

      asm volatile("bar.sync 0, 384;" ::: "memory");
#pragma unroll 1
      for (int i = 0; i < 4; i++) {
        const uint64_t dx = d128(dX + i * 2048), df = d128(dK + (OFF_XB >> 4) + (i & 1) * 1024);
        mbar_wait(bars + 8 * (B_FX + 2 * i), 0);
        wg_fence();
        mma_ss64<0, 0, 2>(cX, df, dx, i);
        mma_ss64<0, 0, 1>(cX, df + 2, dx + 2);
        wg_commit(); wg_wait<1>();
        mbar_arrive_if(elect && i, bars + 8 * (B_EA + rslot(i - 1)));
        mma_ss64<0, 0, 1>(cX, df + 4, dx + 4);
        mma_ss64<0, 0, 1>(cX, df + 6, dx + 6);
        if (i == 0 && tid == 0) PROF_EV(1);
        mbar_wait(bars + 8 * (B_FX + 2 * i + 1), 0);
        wg_fence();
#pragma unroll
        for (int k = 0; k < 4; k++) mma_ss64<0, 0, 1>(cX, df + (512 + k * 2), dx + (1024 + k * 2));
        wg_commit();
        waitA(i);
        wg_fence();
        const uint64_t da = d128(dX + i * 1024), db = d128(dN + RING + i * 1024);
        mma_ss128<0, 1, 2>(cA, da, db, i);
        wg_commit(); wg_wait<1>();
        mbar_arrive_if(elect, bars + 8 * (B_FE + i));
#pragma unroll
        for (int k = 1; k < 4; k++) mma_ss128<0, 1, 1>(cA, da + k * 2, db + k * 128);
        wg_commit();
      }
      fence_regs<0, 32>(cX);
#pragma unroll
      for (int e = 0; e < 16; e++) yf[e] = pack_pin(cX[2 * e], cX[2 * e + 1]);
      if (tid == 0) { PROF_EV(2); PROF_CK(42); }
      {
        waitA(4); mbar_wait(bars + 8 * B_E0, 0);
        const uint64_t de = d128(dN + (wg ? RING : OFF_XB >> 4));
        wg_fence();
        mma_rs128<0, 1, 0>(cB, yf[0], yf[1], yf[2], yf[3], de);
        wg_commit();
        wg_wait<1>();
        freeA(3);
#pragma unroll
        for (int k = 1; k < 4; k++) mma_rs128<0, 1, 1>(cB, yf[4 * k], yf[4 * k + 1], yf[4 * k + 2], yf[4 * k + 3], de + k * 128);
        wg_commit();
      }
      bool rel = false;
      auto acquire = [&](int n) {
        rel = elect;
        if (!mbar_try(bars + 8 * (B_FA + rslot(n)), rpar(n))) { wg_wait<0>(); freeA(n - 1); rel = false; waitA(n); }
      };
      auto freeP = [&](int n) { mbar_arrive_if(rel, bars + 8 * (B_EA + rslot(n - 1))); };
      auto ffn_step = [&](auto first, auto split, float (&acc)[64], int n, int kb, auto done, auto work) {
        constexpr int SPLIT = decltype(split)::value;
        acquire(n);
        wg_fence();
        const uint64_t dx = d128(dX + kb * 1024), db = d128(dN + RING + rslot(n) * 1024);
        mma_ss128<0, 1, decltype(first)::value>(acc, dx, db, kb);
#pragma unroll
        for (int k = 1; k < SPLIT; k++) mma_ss128<0, 1, 1>(acc, dx + k * 2, db + k * 128);
        wg_commit();
        work();
        wg_wait<1>();
        freeP(n);
        done();
        if (SPLIT < 4) {
          wg_fence();
#pragma unroll
          for (int k = SPLIT; k < 4; k++) mma_ss128<0, 1, 1>(acc, dx + k * 2, db + k * 128);
          wg_commit();
        }
      };
      {
        const int s0 = 2 * rb + wg, kr = 2 * ((s0 & 1) | ((s0 & 4) >> 1));
        const int m = lane >> 3, r = lane & 7;
        const uint32_t a0 = sb + OFF_XB + wg * 8192 + (((w >> 1) * 8 + (m >> 1)) * 2 + (w & 1)) * 256 + (m & 1) * 128 + ((r ^ (kr + (m & 1))) << 4);
        ffn_step(IC<1>(), IC<4>(), cA, 5, 4, [&] { fence_regs<0, 64>(cB); }, nop);
        asm volatile("bar.sync 5, 256;" ::: "memory");
        auto stage = [&](int i) {
          stsm4t(a0 + i * 1024, pack_bf16(cB[8 * i] - cB[34 + 8 * i], cB[8 * i + 1] - cB[35 + 8 * i]),
                 pack_bf16(cB[32 + 8 * i] + cB[8 * i + 2], cB[33 + 8 * i] + cB[8 * i + 3]),
                 pack_bf16(cB[8 * i + 4] - cB[38 + 8 * i], cB[8 * i + 5] - cB[39 + 8 * i]),
                 pack_bf16(cB[36 + 8 * i] + cB[8 * i + 6], cB[37 + 8 * i] + cB[8 * i + 7]));
          if (j == 0 && w == 0) {
            const uint32_t a1 = r ? sb + OFF_SP + 1024 : sb + OFF_SP + wg * 512 + (m & 1) * 256 + (m >> 1) * 128;
#pragma unroll
            for (int n = 2 * i; n < 2 * i + 2; n++)
              asm volatile("stmatrix.sync.aligned.m8n8.x4.shared.b16 [%0], {%1,%2,%3,%4};" ::"r"(a1 + ((n ^ (kr + (m >> 1)) ^ r) << 4)),
                           "r"(pack_bf16(cB[4 * n], cB[4 * n + 1])), "r"(pack_bf16(cB[4 * n + 2], cB[4 * n + 3])),
                           "r"(pack_bf16(cB[32 + 4 * n], cB[33 + 4 * n])), "r"(pack_bf16(cB[34 + 4 * n], cB[35 + 4 * n])) : "memory");
          }
        };
        auto publish = [&] {
          asm volatile("fence.proxy.async.shared::cta;" ::: "memory");
          __syncwarp();
          mbar_arrive_if(lane == 0, bars + 8 * (B_XS + wg));
          if (tid == 0) PROF_EV(3);
        };
        stage(0);
        ffn_step(IC<1>(), IC<FSPLIT>(), cA, 6, 5, nop, nop);
        stage(1);
        ffn_step(IC<1>(), IC<FSPLIT>(), cA, 7, 6, nop, nop);
        stage(2);
        ffn_step(IC<1>(), IC<2>(), cA, 8, 7, [&] { stage(3); }, nop);
        publish();
      }
      uint32_t gb0 = 0, gb1 = 0;
      uint32_t ob[2] = {0, 0};
      auto glu = [&](auto& acc, int half, int ho, int i0, int i1) {
#pragma unroll
        for (int i = i0; i < i1; i++)
          asm volatile("{\n.reg .b32 a, b;\ncvt.rn.relu.bf16x2.f32 a, %2, %1;\ncvt.rn.bf16x2.f32 b, %4, %3;\nmul.rn.bf16x2 a, a, b;\nmul.rn.bf16x2 %0, a, %5;\n}"
                       : "=r"(h[ho + i]) : "f"(acc[2 * i]), "f"(acc[2 * i + 1]), "f"(acc[half + 2 * i]), "f"(acc[half + 1 + 2 * i]), "r"(ob[i & 1]) : "memory");
      };
      ffn_step(IC<2>(), IC<1>(), cB, 9, zero, nop, nop);
#pragma unroll 1
      for (int kb = 1; kb < 8; kb++)
        ffn_step(IC<1>(), IC<FSPLIT>(), cB, 9 + kb, kb, nop, [&] {
          if (kb == GKB) {
            mbar_wait(bars + 8 * B_G, 0);
            asm volatile("ld.shared.u32 %0, [%2];\nld.shared.u32 %1, [%2+32];" : "=r"(gb0), "=r"(gb1) : "r"(sb + OFF_G + (wg * 64 + w * 16 + g) * 4) : "memory");
          } else if (kb == 5 + 2 * wg) {
            ob[0] = pack_bf16(1.0f - bf_hi(gb0), 1.0f - bf_hi(gb0)); ob[1] = pack_bf16(1.0f - bf_hi(gb1), 1.0f - bf_hi(gb1));
            glu(cA, 32, 0, 0, 16);
          }
        });
      const uint32_t tag = gb0 & 1;
      const float g0 = bf_hi(gb0), g1 = bf_hi(gb1);
      if (tid == 0) { PROF_EV(4); PROF_CK(43); }
      auto m_step = [&](auto first, int i) {
        acquire(17 + i);
        wg_fence();
        const uint64_t dx = d128(dX + i * 2048), dm = d64(dN + RING + rslot(17 + i) * 1024);
        mma_ss64<0, 1, decltype(first)::value>(ct, dx, dm);
#pragma unroll
        for (int k = 1; k < MSPLIT; k++) mma_ss64<0, 1, 1>(ct, dx + ((k >> 2) * 1024 + (k & 3) * 2), dm + k * 64);
        wg_commit();
        wg_wait<1>();
        freeP(17 + i);
        wg_fence();
#pragma unroll
        for (int k = MSPLIT; k < 8; k++) mma_ss64<0, 1, 1>(ct, dx + ((k >> 2) * 1024 + (k & 3) * 2), dm + k * 64);
        wg_commit();
      };
      m_step(IC<0>(), 0);
#pragma unroll 1
      for (int i = 1; i < 5; i++) {
        if (i == 1 + 2 * wg) glu(cB, 32, 16, 0, 16);
        if (i < 4) m_step(IC<1>(), i);
      }
      if (tid == 0) { PROF_EV(5); PROF_CK(44); }
      ffn_step(IC<0>(), IC<1>(), cC, 21, 0, nop, nop);
#pragma unroll 1
      for (int kb = 1; kb < 8; kb++)
        ffn_step(IC<1>(), IC<FSPLIT>(), cC, 21 + kb, kb, [&] { mbar_arrive_if(elect && !(kb & 1), bars + 8 * (B_ET + (kb >> 1) - 1)); }, [&] {
          if (kb == 1 + wg) glu(ct, 16, 48, 0, 8);
        });

      auto twait = [&](uint32_t bar, uint32_t par, int) { mbar_wait(bar, par); };
      const int fo = warp * 128 + lane;
      auto fetch = [&](uint4 (&pv)[4], int z) {
        twait(bars + 8 * (z < 4 ? B_Z + 2 * z + wg : z < 6 ? B_HP + z - 4 : B_HP + 2 + wg), 0, 8 + z);
        const uint8_t* src = smem + (z < 4 ? OFF_Z - z * U : z == 4 ? OFF_T : (z - 5) * U) + fo * 16;
#pragma unroll
        for (int i = 0; i < 4; i++) pv[i] = *(const uint4*)(src + i * 512);
      };
      const uint32_t peerZ = mapa(sb + OFF_Z + fo * 16, rank ^ 1), peerB = mapa(bars + 8 * (B_Z + wg), rank ^ 1);
      auto tile_mma = [&](auto off, int t, int k0, int k1, int init) {
        constexpr int O = decltype(off)::value;
        const uint64_t db = d128(dN + (t & 3) * (TB >> 4)), dw = db + rank * 256, dm = db + (rank ? 0 : 1536);
#pragma unroll
        for (int k = k0; k < k1; k++) {
          if (k == 0) mma_rs64<O, 1, 2>(ct, h[0], h[1], h[2], h[3], dw, init);
          else if (k < 14) mma_rs64<O, 1, 1>(ct, h[4 * k], h[4 * k + 1], h[4 * k + 2], h[4 * k + 3], k < 12 ? dw + k * 128 : dm + (k - 12) * 128);
          else mma_rs64<O, 1, 1>(ct, yf[4 * k - 56], yf[4 * k - 55], yf[4 * k - 54], yf[4 * k - 53], db + k * 128);
        }
      };
      uint4 pv[4] = {};
      auto tile = [&](auto off, int t) {
        constexpr int P = 32 - decltype(off)::value;
        const bool grid = t >= 4 && t < 7, pre = t >= 3 && t != 6;
        const int zo = grid ? t - 4 : t == 7 ? 3 : t - 1, z = t - 3;
        const int owner = rb * 8 + 2 * ((q4 + zo + 1) & 3) + rank;
        uint4* dst = ws->part + (size_t)(owner * 3 + zo) * 1024 + fo;
        const uint32_t src = sb + (z < 4 ? OFF_Z - z * U : OFF_T) + fo * 16;
        twait(bars + 8 * (B_FT + (t & 3)), t >> 2, t);
        wg_fence();
        tile_mma(off, t, 0, TH, zero);
        wg_commit();
        wg_wait<1>();
        mbar_arrive_if(elect && t < 6, bars + 8 * (B_ET + t - 1));
        if (t < 3) twait(bars + 8 * (t == 1 ? B_RD0 : B_RDY), 0, 14 + t);
        fence_regs<P, 32>(ct);
#pragma unroll
        for (int i = 0; i < 4; i++) {
          pv[i].x = (add_bf2(pv[i].x, pack_bf16(ct[P + 8 * i], ct[P + 8 * i + 1])) & ~(uint32_t)grid) | (tag & grid);
          pv[i].y = add_bf2(pv[i].y, pack_bf16(ct[P + 8 * i + 2], ct[P + 8 * i + 3]));
          pv[i].z = add_bf2(pv[i].z, pack_bf16(ct[P + 8 * i + 4], ct[P + 8 * i + 5]));
          pv[i].w = add_bf2(pv[i].w, pack_bf16(ct[P + 8 * i + 6], ct[P + 8 * i + 7]));
        }
        if (grid) {
#pragma unroll
          for (int i = 0; i < 4; i++)
            asm volatile("st.relaxed.gpu.global.v4.u32 [%0], {%1,%2,%3,%4};" ::"l"(dst + i * 32), "r"(pv[i].x), "r"(pv[i].y), "r"(pv[i].z), "r"(pv[i].w) : "memory");
          hint_add_if(lane == 0, &ws->cntP[32 * owner + 8 * (zo + (zo == 2 ? wg : 0))]);
        }
        auto share = [&](int i) {
          asm volatile("st.async.weak.shared::cluster.mbarrier::complete_tx::bytes.v4.b32 [%0], {%2,%3,%4,%5}, [%1];" ::"r"(peerZ - zo * U + i * 512),
                       "r"(peerB + 16 * zo), "r"(pv[i].x), "r"(pv[i].y), "r"(pv[i].z), "r"(pv[i].w) : "memory");
        };
        if (P == 0 && t == 7) { share(1); share(2); share(3); }
#pragma unroll
        for (int i = 0; i < 4; i++) {
          if (i == 0 ? !grid : t < 4) share(i);
          wg_fence();
          tile_mma(off, t, TH + SPC * i, i < 3 ? TH + SPC * i + SPC : TL, 0);
        }
        wg_commit();
        if (pre) twait(bars + 8 * (z < 4 ? B_Z + 2 * z + wg : B_HP), 0, 8 + z);
        wg_fence();
#pragma unroll
        for (int i = 0; i < 4; i++) {
          asm volatile("{\n.reg .pred p;\nsetp.ne.b32 p, %5, 0;\nmov.b32 %0, 0;\nmov.b32 %1, 0;\nmov.b32 %2, 0;\nmov.b32 %3, 0;\n@p ld.shared.v4.u32 {%0,%1,%2,%3}, [%4];\n}"
                       : "=r"(pv[i].x), "=r"(pv[i].y), "=r"(pv[i].z), "=r"(pv[i].w) : "r"(src + i * 512), "r"((int)pre) : "memory");
          tile_mma(off, t, TL + i, i < 3 ? TL + 1 + i : 18, 0);
        }
        wg_commit();
      };
      asm volatile("barrier.cluster.wait.aligned;" ::: "memory");
      twait(bars + 8 * B_FT, 0, 0);
      wg_fence();
      tile_mma(IC<0>(), 0, 0, T0A, zero);
      wg_commit();
      waitA(29 + wg);
      wg_wait<1>();
      mbar_arrive_if(elect, bars + 8 * (B_ET + 3));
      glu(cC, 32, 32, 0, 16);
      if (tid == 0) PROF_EV(6);
      if (tid == 128) PROF_EV(27);
      mbar_wait(bars + 8 * (j == 0 ? B_T : B_TL), 0);
      if (tid == 0) { PROF_EV(7); PROF_CK(45); }
      wg_fence();
      {
        const uint64_t dt = d128(dN + (OFF_T >> 4) + wg * 512), de = d128(dK + RING + (1 + wg) * 1024);
        mma_ss64<0, 1, 0>(ci, de, dt);
        mma_ss64<32, 1, 0>(ci, de + 512, dt);
#pragma unroll
        for (int k = 1; k < 4; k++) {
          mma_ss64<0, 1, 1>(ci, de + k * 2, dt + k * 128);
          mma_ss64<32, 1, 1>(ci, de + (512 + k * 2), dt + k * 128);
        }
        wg_commit();
      }
      tile_mma(IC<0>(), 0, T0A, 14, 0);
      wg_commit();
      wg_wait<1>();
      if (elect) asm volatile("mbarrier.arrive.shared::cluster.b64 _, [%0];" ::"r"(mapa(bars + 8 * B_RDY, rank ^ 1)) : "memory");
      mbar_arrive_if(elect, bars + 8 * (B_PZ + 1));
      fence_regs<0, 64>(ci);
#pragma unroll
      for (int i = 0; i < 16; i++) {
        const float gg = ((i & 1) ? g1 : g0) * (2.0f / (2048.0f * 512.0f));
        if (i & 2) yf[i] = pack_pin((ci[2 * i] - ci[28 + 2 * i]) * gg, (ci[2 * i + 1] - ci[29 + 2 * i]) * gg);
        else yf[i] = pack_pin((ci[2 * i] + ci[36 + 2 * i]) * gg, (ci[2 * i + 1] + ci[37 + 2 * i]) * gg);
      }
      wg_fence();
      tile_mma(IC<0>(), 0, 14, 18, 0);
      wg_commit();
      if (tid == 0) PROF_EV(8);
      if (tid == 128) PROF_EV(28);
#pragma unroll 1
      for (int t = 1;; t += 2) {
        tile(IC<32>(), t);
        if (t == 7) break;
        tile(IC<0>(), t + 1);
      }
      if (tid == 0) { PROF_EV(9); PROF_CK(46); }
      if (tid == 128) PROF_EV(29);
      {
        uint4 p1[4], p2[4];
        auto acc4 = [&](uint4 (&d)[4], const uint4 (&a)[4]) {
#pragma unroll
          for (int i = 0; i < 4; i++) { d[i].x = add_bf2(d[i].x, a[i].x); d[i].y = add_bf2(d[i].y, a[i].y); d[i].z = add_bf2(d[i].z, a[i].z); d[i].w = add_bf2(d[i].w, a[i].w); }
        };
        auto check = [&](uint4 (&a)[4], uint4 (&b)[4], int za, int zb) {
          auto stale = [&] {
            uint32_t bad = 0;
#pragma unroll
            for (int i = 0; i < 4; i++) bad |= (a[i].x ^ tag) | (b[i].x ^ tag);
            return __any_sync(0xffffffffu, bad & 1);
          };
          const uint4* src = ws->part + (size_t)(rb * 8 + j) * 3 * 1024 + fo;
#pragma unroll 1
          for (int n = 0; stale(); n++) {
#pragma unroll
            for (int i = 0; i < 4; i++) { a[i] = ld_x4(src + za * 1024 + i * 32); if (za != zb) b[i] = ld_x4(src + zb * 1024 + i * 32); }
            if (n > (1 << 21)) __trap();
          }
#pragma unroll
          for (int i = 0; i < 4; i++) { a[i].x &= ~1u; b[i].x &= ~1u; }
        };
        auto add32 = [&](const uint4 (&a)[4]) {
#pragma unroll
          for (int i = 0; i < 4; i++) {
            const uint32_t u[4] = {a[i].x, a[i].y, a[i].z, a[i].w};
#pragma unroll
            for (int e = 0; e < 4; e++) { ct[32 + 8 * i + 2 * e] += bf_lo(u[e]); ct[33 + 8 * i + 2 * e] += bf_hi(u[e]); }
          }
        };
        fetch(p1, 5);
        fetch(p2, 3);
        if (tid == 0) PROF_EV(25);
        wg_wait<0>();
        fence_regs<32, 32>(ct);
        check(pv, p1, 0, 1);
        acc4(p1, p2); acc4(pv, p1);
        add32(pv);
        fence_regs<32, 32>(ct);
        fetch(p2, 6);
        if (tid == 0) PROF_EV(24);
        check(p2, p2, 2, 2);
        add32(p2);
#pragma unroll
        for (int i = 0; i < 4; i++)
          pv[i] = make_uint4(pack_bf16(ct[32 + 8 * i], ct[33 + 8 * i]), pack_bf16(ct[34 + 8 * i], ct[35 + 8 * i]), pack_bf16(ct[36 + 8 * i], ct[37 + 8 * i]), pack_bf16(ct[38 + 8 * i], ct[39 + 8 * i]));
        if (tid == 0) PROF_EV(14);
        const uint32_t stg = sb + OFF_T + warp * 2048;
        const int mr = (lane & 7) + ((lane >> 3) & 1) * 8, mc = lane >> 4;
#pragma unroll
        for (int i = 0; i < 4; i++)
          asm volatile("stmatrix.sync.aligned.m8n8.x4.shared.b16 [%0], {%1,%2,%3,%4};" ::"r"(stg + mr * 128 + (((2 * i + mc) ^ (mr & 7)) << 4)), "r"(pv[i].x),
                       "r"(pv[i].y), "r"(pv[i].z), "r"(pv[i].w) : "memory");
        __syncwarp();
#pragma unroll
        for (int i = 0; i < 4; i++) {
          const int r = 4 * i + (lane >> 3), c = lane & 7;
          const uint4 v = *(const uint4*)(smem + OFF_T + warp * 2048 + r * 128 + ((c ^ (r & 7)) << 4));
          *(uint4*)(out + (size_t)(2 * rb + wg + 32 * (16 * w + r)) * 512 + 64 * j + 8 * c) = v;
        }
      }
      if (tid == 0) { PROF_EV(15); PROF_CK(41); }
      if (tid == 128) PROF_EV(30);
    }
  } else if (warp < 12) {
    asm volatile("setmaxnreg.dec.sync.aligned.u32 104;");
    asm volatile("barrier.cluster.arrive.relaxed.aligned;" ::: "memory");
    const int t = tid - 256, w = warp - 8;
    const uint32_t ep = ld_x1(&ws->epoch[blockIdx.x * 8]);
    const uint32_t tag = (ep + 1) & 1;
    auto w_issue = [&](const CUtensorMap* m) {

      if (elect_one()) { mbar_expect_tx(bars + 8 * (B_WR + w), 3072); tma4d(sb + OFF_T + w * 3072, m, bars + 8 * (B_WR + w), 16 * kg, 0, 2 * w, tn); }

          __syncwarp();
    };
    auto gate_rows = [&] {
      const int r = 16 * j + 4 * w + (lane >> 3);
      const uint4* pg = (const uint4*)gate_w + (lane & 7);
      {
        float a = 0.f;
        asm volatile("bar.sync 4, 256;" ::: "memory");
#pragma unroll 1
        for (int hf = 0; hf < 2; hf++) {
          uint4 v[4], u[4];
#pragma unroll
          for (int kb = 0; kb < 4; kb++) v[kb] = __ldg(pg + (4 * hf + kb) * 8);
          mbar_wait(bars + 8 * (B_FE + 1 + 2 * hf), 0);
          if (hf) w_issue(&maps.wr);
#pragma unroll
          for (int kb = 0; kb < 4; kb++) u[kb] = *(const uint4*)(smem + (4 * hf + kb) * U + r * 128 + (((lane ^ r) & 7) << 4));
#pragma unroll
          for (int kb = 0; kb < 4; kb++) {
            const uint32_t uu[4] = {u[kb].x, u[kb].y, u[kb].z, u[kb].w}, vv[4] = {v[kb].x, v[kb].y, v[kb].z, v[kb].w};
#pragma unroll
            for (int e = 0; e < 4; e++) {
              uint32_t pr;
              asm("mul.rn.bf16x2 %0, %1, %2;" : "=r"(pr) : "r"(uu[e]), "r"(vv[e]));
              a += bf_lo(pr) + bf_hi(pr);
            }
          }
        }
#pragma unroll
        for (int o = 4; o; o >>= 1) a += __shfl_xor_sync(0xffffffffu, a, o);
        if ((lane & 7) == 0)
          asm volatile("st.relaxed.gpu.global.u32 [%0], %1;" ::"l"(ws->gate + rb * 128 + r),
                       "r"(pack_bf16(0.f, __fdividef(1.0f, 1.0f + __expf(-bf_lo(pack_bf16(a, 0.f))))) | tag) : "memory");
        if (t == 0) PROF_EV(18);
      }
    };
    {
      const int g = lane >> 2, q = lane & 3;
      uint32_t wf[32];
      if (!helper) {
        gate_rows();
        const uint32_t wa = sb + OFF_T + w * (3072 + 4) + q * 48 + g * 2;
#pragma unroll 1
        for (int ri = 0; ri < 2; ri++) {
          mbar_wait(bars + 8 * (B_WR + w), ri);
#pragma unroll
          for (int n2 = 0; n2 < 32 / WB; n2++) {
            uint32_t v[WB];
#pragma unroll
            for (int i = 0; i < WB; i++) {
              const int e = n2 * WB + i;
              asm volatile("ld.shared.u16 %0, [%1];" : "=r"(v[i]) : "r"(wa + ((e >> 1) & 7) * 192 + (e & 1) * (1536 + 2) + (e >> 4) * 16) : "memory");
            }
#pragma unroll
            for (int i = 0; i < WB; i++) wf[n2 * WB + i] = __byte_perm(wf[n2 * WB + i], v[i], 0x5432);
            if (WSLEEP) { asm volatile("nanosleep.u32 %0;" ::"r"(WSLEEP + (v[WB - 1] >> 16)) : "memory"); }
          }
          __syncwarp();
          if (ri == 0) w_issue(&maps.wi);
        }
        asm volatile("bar.sync 1, 128;" ::: "memory");
        if (t == 0) PROF_EV(11);
      } else {
        asm volatile("bar.sync 4, 256;" ::: "memory");
        hint_wait(&ws->cntW[0], (ep + 1) * 128u);
        const uint32_t t0 = (uint32_t)clock();
#pragma unroll 1
        for (;;) {
          uint32_t bad = 0;
#pragma unroll
          for (int i = 0; i < 32; i++) {
            const float2 v = ld_x2((const float2*)ws->Wh + (i >> 4) * 2048 + 16 * w + g + 8 * (i & 1) + 64 * q + ((i >> 1) & 7) * 256);
            wf[i] = __float_as_uint(v.x); bad |= __float_as_uint(v.y) ^ tag;
          }
          if (!__any_sync(0xffffffffu, bad & 1)) break;
          spin_guard(t0);
        }
        if (t == 0) PROF_EV(11);
      }
      if (w == 0 && elect_one()) { mbar_expect_tx(bars + 8 * B_W, 8192); bulk_load(sb + OFF_D, dtab, 8192, bars + 8 * B_W); }
      asm volatile("barrier.cluster.wait.aligned;" ::: "memory");
      mbar_wait(bars + 8 * B_W, 0);
      mbar_wait(bars + 8 * B_HX, 0);
      if (t == 0) PROF_EV(12);
      const uint32_t dd = (sb & 0x3FFFF) >> 4;
      const uint64_t dF = d128((dd + (OFF_D >> 4)) | (512u << 16)), dI = d128((dd + (OFF_D >> 4)) | (1u << 16)), dA = d128((dd + (OFF_XB >> 4)) | (512u << 16));
      float az[32];
      const int zero = blockIdx.x >> 16;
      uint32_t pf[32];
#pragma unroll
      for (int mt = 0; mt < 2; mt++) {
        wg_fence();
        if (mt == 0) mma_ss64<0, 3, 0>(az, dA, dF);
        else mma_ss64<0, 3, 2>(az, dA + 512, dF, zero);
#pragma unroll
        for (int k = 1; k < 4; k++) mma_ss64<0, 3, 1>(az, dA + (mt * 512 + k * 128), dF + k * 128);
        wg_commit();
        wg_wait<0>();
        fence_regs<0, 32>(az);
#pragma unroll
        for (int i = 0; i < 16; i++) {
          const float wr = bf_lo(wf[16 * mt + i]), wi = bf_hi(wf[16 * mt + i]);
          pf[16 * mt + i] = pack_pin(fmaf(az[2 * i], wr, -az[2 * i + 1] * wi), fmaf(az[2 * i], wi, az[2 * i + 1] * wr));
        }
      }
      if (t == 0) PROF_EV(16);
      {
        const int m = lane >> 3, r = lane & 7;
        const int sl = 2 * (m >> 1) + ((r >> 1) & 1) + 4 * (r >> 2);
        const uint32_t a0 = sb + OFF_XB + (2 * w + (m & 1)) * 2048 + sl * 64;
        uint32_t pk[16];
#pragma unroll
        for (int mt = 0; mt < 3; mt++) {
          if (mt < 2) {
            wg_fence();
            mma_rs64<0, 0, 2>(az, pf[16 * mt], pf[16 * mt + 1], pf[16 * mt + 2], pf[16 * mt + 3], dI, mt ? (int)helper : zero);
#pragma unroll
            for (int k = 1; k < 4; k++) mma_rs64<0, 0, 1>(az, pf[16 * mt + 4 * k], pf[16 * mt + 4 * k + 1], pf[16 * mt + 4 * k + 2], pf[16 * mt + 4 * k + 3], dI + k * 2);
            wg_commit();
          }
          if (mt > 0 && !helper) {
#pragma unroll
            for (int i = 0; i < 4; i++) stsm4t(a0 + ((((mt - 1) * 2 + (r & 1)) ^ (sl >> 1)) << 4) + i * 512, pk[4 * i], pk[4 * i + 1], pk[4 * i + 2], pk[4 * i + 3]);
          }
          if (mt < 2) {
            wg_wait<0>();
            fence_regs<0, 32>(az);
#pragma unroll
            for (int i = 0; i < 16; i++) pk[i] = pack_pin(az[2 * i], az[2 * i + 1]);
          }
        }
      }
      if (helper) {
#pragma unroll
        for (int i = 0; i < 16; i++) {
          const int n = i >> 1, s0 = 8 * (n >> 1) + 2 * (n & 1) + (q & 1) + 4 * (q >> 1);
          if ((n & 1) == (int)(blockIdx.x & 1)) st_u2(ws->Ts + s0 * 64 + 16 * w + g + 8 * (i & 1), pack_bf16(az[2 * i], az[2 * i + 1]), tag);
        }
        __syncwarp();
        hint_add_if(lane == 0, &ws->cntH[0]);
        if (t == 0) { ws->epoch[blockIdx.x * 8] = ep + 1; PROF_EV(13); }
      } else {
        asm volatile("fence.proxy.async.shared::cta;" ::: "memory");
        __syncwarp();
        if (elect_one()) {
          if (t == 0) PROF_EV(17);
          if (SPACE) __nanosleep(SPACE * w);
          asm volatile("cp.async.bulk.tensor.3d.global.shared::cta.bulk_group [%0, {%2, %3, %4}], [%1];" ::"l"(&maps.ts), "r"(sb + OFF_XB + w * 4096),
                       "r"(32 * kg), "r"(0), "r"(8 * tn + 2 * w) : "memory");
          bulk_done_signal(&ws->cntT[32 * j]);
          asm volatile("mbarrier.arrive.shared::cluster.b64 _, [%0];" ::"r"(mapa(bars + 8 * B_RD0, rank ^ 1)) : "memory");
          if (t == 96) PROF_EV(13);
        }
        __syncwarp();
        if (j == 0) {
          hint_wait(&ws->cntH[0], (ep + 1) * 8u);
          const uint32_t t0 = (uint32_t)clock();
          float2 v;
          do { v = ld_x2((const float2*)ws->Ts + 2 * rb * 64 + t); spin_guard(t0); } while (__any_sync(0xffffffffu, (__float_as_uint(v.y) ^ tag) & 1));
          mbar_wait(bars + 8 * B_TL, 0);
          const uint32_t u = __float_as_uint(v.x);
          *(uint16_t*)(smem + OFF_T + t * 128 + ((t & 7) << 4)) = (uint16_t)u;
          *(uint16_t*)(smem + OFF_T + t * 128 + (((t & 7) ^ 1) << 4)) = (uint16_t)(u >> 16);
          asm volatile("fence.proxy.async.shared::cta;" ::: "memory");
          __syncwarp();
          mbar_arrive_if(lane == 0, bars + 8 * B_T);
        }
      }
    }
  } else {
    asm volatile("setmaxnreg.dec.sync.aligned.u32 24;");
    auto xf_load = [&](int q) {
      const uint32_t fb = bars + 8 * (B_FX + q);
      mbar_expect_tx(fb, U + 8192);
      tma3d(sb + q * U, &maps.x, fb, 64 * q, 0, 2 * rb);
      if (q >= 4) mbar_wait(bars + 8 * (B_FE + ((q - 4) >> 1)), 0);
      tma2d(sb + OFF_XB + (q & 3) * 8192, &maps.ft, fb, 64 * q, 64 * j);
    };
    if (elect_one()) {
      if (warp == 14) {
#pragma unroll
        for (int i = 0; i < B_FT; i++) mbar_init(bars + 8 * i, 1);
        asm volatile("fence.mbarrier_init.release.cluster;" ::: "memory");
        if (!helper) {
#pragma unroll 1
          for (int n = 0; n < 2; n++) {
            const uint32_t fb = bars + 8 * (B_FA + n);
            xf_load(2 * n); xf_load(2 * n + 1);
            mbar_expect_tx(fb, U);
            tma2d(sb + OFF_RING + n * U, &maps.g64, fb, f_full, 64 * n);
            tma2d(sb + OFF_RING + n * U + 8192, &maps.u64, fb, f_full, 64 * n);
          }
        }
      } else if (warp == 15) {
#pragma unroll
        for (int i = B_FT; i < NBAR; i++) mbar_init(bars + 8 * i, i < B_EA ? 1 : i < B_T ? 2 : 4);
#pragma unroll
        for (int i = 0; i < 8; i++) mbar_expect_tx(bars + 8 * (B_Z + i), U / 2);
        asm volatile("fence.mbarrier_init.release.cluster;" ::: "memory");
        asm volatile("fence.proxy.async.shared::cta;" ::: "memory");
      }
    }
    __syncwarp();
    asm volatile("bar.arrive 0, 384;" ::: "memory");
    asm volatile("bar.arrive 4, 256;" ::: "memory");
    __syncwarp();
    asm volatile("barrier.cluster.arrive.relaxed.aligned;" ::: "memory");
    asm volatile("bar.sync 3, 128;" ::: "memory");
    if (warp == 15 && !helper) {
        mbar_wait(bars + 8 * B_FE, 0);
        const uint32_t tag = (ld_x1(&ws->epoch[blockIdx.x * 8]) + 1) & 1;
        const int c = lane >> 4, jj = 16 * blockIdx.x + (lane & 15), jm = (2048 - jj) & 2047;
        const unsigned short* pr = (const unsigned short*)w_r + 256 * c;
        const unsigned short* pi = (const unsigned short*)w_i + 256 * c;
        const float wr = 0.25f * (bf_lo(__ldg(pr + jj * 257)) + bf_lo(__ldg(pr + jm * 257)));
        const float wi = 0.25f * (bf_lo(__ldg(pi + jj * 257)) - bf_lo(__ldg(pi + jm * 257)));
        st_u2(ws->Wh + c * 2048 + jj, c ? pack_bf16(-wi, wr) : pack_bf16(wr, wi), tag);
        __syncwarp();
        hint_add_if(lane == 0, &ws->cntW[0]);
        mbar_wait(bars + 8 * B_XS, 0);
        const uint32_t t0 = (uint32_t)clock();
        uint4 v;
        do { v = ld_x4(ws->gate + rb * 128 + 4 * lane); spin_guard(t0); } while (__any_sync(0xffffffffu, ((v.x ^ tag) | (v.y ^ tag) | (v.z ^ tag) | (v.w ^ tag)) & 1));
        *(uint4*)(smem + OFF_G + lane * 16) = v;
        __syncwarp();
        mbar_arrive_if(lane < 4, bars + 8 * B_G);
      }
    auto part_load = [&](int i, unsigned ep1) {
      const uint32_t bytes = i < 2 ? U : U / 2;
      mbar_wait(bars + 8 * (B_PZ + (i == 0)), 0);
      mbar_expect_tx(bars + 8 * (B_HP + i), bytes);
      flag_wait(&ws->cntP[32 * (rb * 8 + j) + 8 * i], ep1 * (i < 2 ? 8u : 4u));
      bulk_load(sb + (i == 0 ? OFF_T : i == 1 ? 0 : i * (U / 2)), ws->part + (size_t)(rb * 8 + j) * 3072 + (i < 2 ? i * 1024 : 1024 + i * 512), bytes, bars + 8 * (B_HP + i));
      if (i == 2) PROF_EV(26);
    };
    if ((!helper || warp == 15) && elect_one()) {
      if (warp < 14) {
        const int p = warp - 12;
#pragma unroll 1
        for (int i = 4 + p; i < 13; i += 2) asm volatile("prefetch.tensormap [%0];" ::"l"((const char*)&maps + i * 128) : "memory");
#pragma unroll 1
        for (int n = 2; n < 31; n++) {
          const bool table = n == 4 || n >= 29;
          const bool half = n >= 17 && n < 21;
          const int q = n < 4 ? n : n < 17 ? n - 1 : n - 5;
          const CUtensorMap* m = table ? &maps.e : half ? &maps.g32 + p : &maps.g64 + p;
          const int c0 = table ? 0 : half ? f_half : f_full + 64 * (q >> 3);
          const int c1 = table ? (2 * rb + ((n & 1) ^ 1)) * 128 + 64 * p : half ? 128 * (n - 17) : 64 * (q & 7);
          const uint32_t fb = bars + 8 * (B_FA + (n & 3)), dst = sb + OFF_RING + (n & 3) * U + p * 8192;
          if (n < 4) mbar_wait(bars + 8 * (B_FE + n - 2), 0);
          else mbar_wait(bars + 8 * (B_EA + (n & 3)), ((n >> 2) & 1) ^ 1);
          tma2d(dst, m, fb, c0, c1);
          if (p == 0) mbar_expect_tx(fb, U);
        }
        part_load(2 + p, ld_x1(&ws->epoch[blockIdx.x * 8]) + 1);
      } else if (warp == 15) {
        const unsigned ep1 = ld_x1(&ws->epoch[blockIdx.x * 8]) + 1;
        flag_wait(&ws->cntX[helper ? 0 : 32 * j], ep1 * 16u);
        PROF_EV(22);
        mbar_expect_tx(bars + 8 * B_HX, U);
        bulk_load(sb + OFF_XB, ws->X + (size_t)(helper ? 128 : kg * 8 + tn) * 8192, U, bars + 8 * B_HX);
        if (!helper) {
          flag_wait(&ws->cntT[32 * j], ep1 * 64u);
          PROF_EV(23);
          mbar_expect_tx(bars + 8 * B_TL, U);
          tma3d(sb + OFF_T, &maps.t, bars + 8 * B_TL, 64 * j, 0, 2 * rb);
          part_load(0, ep1); part_load(1, ep1);
          mbar_wait(bars + 8 * (B_HP + 2), 0); mbar_wait(bars + 8 * (B_HP + 3), 0);
          ws->epoch[blockIdx.x * 8] = ep1;
        }
      } else {
#pragma unroll 1
        for (int q = 4; q < 8; q++) xf_load(q);
        mbar_wait(bars + 8 * (B_FE + 2), 0);
        mbar_expect_tx(bars + 8 * B_E0, U);
        tma2d(sb + OFF_XB, &maps.e, bars + 8 * B_E0, 0, 2 * rb * 128);
        tma2d(sb + OFF_XB + 8192, &maps.e, bars + 8 * B_E0, 0, 2 * rb * 128 + 64);
#pragma unroll 1
        for (int h2 = 0; h2 < 2; h2++) {
          const int s0 = 2 * rb + h2, sg = (s0 & ~6) | ((s0 & 2) << 1) | ((s0 & 4) >> 1);
          mbar_wait(bars + 8 * (B_XS + h2), 0);
#pragma unroll 1
          for (int c = 0; c < 2; c++) {
            asm volatile("cp.async.bulk.tensor.4d.global.shared::cta.bulk_group [%0, {%2, %3, %4, %5}], [%1];" ::"l"(&maps.xs),
                         "r"(sb + OFF_XB + h2 * 8192 + c * 4096), "r"(0), "r"(sg), "r"(0), "r"(16 * j + 8 * c) : "memory");
            if (j == 0)
              asm volatile("cp.async.bulk.global.shared::cta.bulk_group [%0], [%1], 256;" ::"l"(ws->X + 128 * 8192 + c * 4096 + sg * 128),
                           "r"(sb + OFF_SP + h2 * 512 + c * 256) : "memory");
            if (SPACE && h2 + c < 2) __nanosleep(SPACE);
          }
        }
        bulk_done_signal(&ws->cntX[32 * j]);
        PROF_EV(20);
#pragma unroll 1
        for (int t = 0; t < 8; t++) {
          const int i = t < 3 ? t + 1 : t < 6 ? t - 2 : 0;
          const int col = 64 * (2 * ((q4 + i) & 3) + ((t < 3 || t == 6) ? 1 - rank : rank));
          const uint32_t fb = bars + 8 * (B_FT + (t & 3)), dst = sb + (t & 3) * TB;
          mbar_wait(bars + 8 * (B_ET + (t < 3 ? t + 1 : t & 3)), t >> 2);
          mbar_expect_tx(fb, TB);
          tma2d(dst, &maps.d224, fb, col, 224 * j);
          if (t < 2) mbar_wait(bars + 8 * (B_ET + t + 1), 0);
          tma2d(dst + 28672, &maps.ft, fb, col, 64 * j);
        }
      }
    }
  }
}

typedef CUresult (*EncodeFn)(CUtensorMap*, CUtensorMapDataType, cuuint32_t, void*, const cuuint64_t*, const cuuint64_t*, const cuuint32_t*,
                             const cuuint32_t*, CUtensorMapInterleave, CUtensorMapSwizzle, CUtensorMapL2promotion, CUtensorMapFloatOOBfill);

static void encode(EncodeFn f, CUtensorMap* m, const void* base, int rank, const cuuint64_t* dims, const cuuint64_t* strides, const cuuint32_t* box,
                   CUtensorMapSwizzle sw) {
  cuuint32_t es[5] = {1, 1, 1, 1, 1};
  f(m, CU_TENSOR_MAP_DATA_TYPE_BFLOAT16, rank, (void*)base, dims, strides, box, es, CU_TENSOR_MAP_INTERLEAVE_NONE, sw,
    CU_TENSOR_MAP_L2_PROMOTION_L2_128B, CU_TENSOR_MAP_FLOAT_OOB_FILL_NONE);
}

extern "C" void kernel_launch(void* const* d_in, const int* in_sizes, int n_in, void* d_out, int out_size) {
  (void)in_sizes; (void)n_in; (void)out_size;
  const __nv_bfloat16* x = (const __nv_bfloat16*)d_in[0];
  const __nv_bfloat16* w_r = (const __nv_bfloat16*)d_in[1];
  const __nv_bfloat16* w_i = (const __nv_bfloat16*)d_in[2];
  const __nv_bfloat16* Wg = (const __nv_bfloat16*)d_in[4];
  const __nv_bfloat16* Wu = (const __nv_bfloat16*)d_in[5];
  const __nv_bfloat16* Wd = (const __nv_bfloat16*)d_in[6];
  const __nv_bfloat16* gw = (const __nv_bfloat16*)d_in[7];

  void* fp = nullptr; cudaDriverEntryPointQueryResult qr;
  cudaGetDriverEntryPoint("cuTensorMapEncodeTiled", &fp, cudaEnableDefault, &qr);
  EncodeFn enc = (EncodeFn)fp;
  void *pFT, *pET, *pDT, *pW;
  cudaGetSymbolAddress(&pDT, g_DT); cudaGetSymbolAddress(&pW, g_work);
  void *pX = ((Work*)pW)->X, *pT = ((Work*)pW)->T;
  cudaGetSymbolAddress(&pFT, g_FT); cudaGetSymbolAddress(&pET, g_ET);

  Maps mp;
  const CUtensorMapSwizzle S128 = CU_TENSOR_MAP_SWIZZLE_128B, S64 = CU_TENSOR_MAP_SWIZZLE_64B;
  { cuuint64_t d[3] = {512, 64, 32}, s[2] = {32768, 1024}; cuuint32_t b[3] = {64, 64, 2}; encode(enc, &mp.x, x, 3, d, s, b, S128); }
  { cuuint64_t d[2] = {512, 512}, s[1] = {1024}; cuuint32_t b[2] = {64, 64}; encode(enc, &mp.ft, pFT, 2, d, s, b, S128); }
  { cuuint64_t d[4] = {128, 32, 2, 129}, s[3] = {256, 8192, 16384}; cuuint32_t b[4] = {128, 1, 2, 8}; encode(enc, &mp.xs, pX, 4, d, s, b, CU_TENSOR_MAP_SWIZZLE_NONE); }
  { cuuint64_t d[3] = {512, 32, 64}, s[2] = {65536, 1024}; cuuint32_t b[3] = {32, 32, 2}; encode(enc, &mp.ts, pT, 3, d, s, b, S64); }
  { cuuint64_t d[3] = {512, 64, 32}, s[2] = {1024, 65536}; cuuint32_t b[3] = {64, 64, 2}; encode(enc, &mp.t, pT, 3, d, s, b, S128); }
  { cuuint64_t d[2] = {64, 4096}, s[1] = {128}; cuuint32_t b[2] = {64, 64}; encode(enc, &mp.e, pET, 2, d, s, b, S128); }
  { cuuint64_t d[2] = {1792, 512}, s[1] = {3584}; cuuint32_t b[2] = {64, 64}, b2[2] = {32, 128};
    encode(enc, &mp.g64, Wg, 2, d, s, b, S128); encode(enc, &mp.u64, Wu, 2, d, s, b, S128);
    encode(enc, &mp.g32, Wg, 2, d, s, b2, S64); encode(enc, &mp.u32, Wu, 2, d, s, b2, S64); }
  { cuuint64_t d[2] = {512, 1792}, s[1] = {1024}; cuuint32_t b[2] = {64, 224}; encode(enc, &mp.d224, Wd, 2, d, s, b, S128); }
  { cuuint64_t d[4] = {264, 32, 8, 8}, s[3] = {32896, 512, 4112}; cuuint32_t b[4] = {24, 32, 2, 1};
    encode(enc, &mp.wr, w_r, 4, d, s, b, CU_TENSOR_MAP_SWIZZLE_NONE); encode(enc, &mp.wi, w_i, 4, d, s, b, CU_TENSOR_MAP_SWIZZLE_NONE); }

  cudaFuncSetAttribute(fused_kernel, cudaFuncAttributeMaxDynamicSharedMemorySize, SMEM_BYTES);
  fused_kernel<<<NCTA, 512, SMEM_BYTES>>>((Work*)pW, (const uint16_t*)pDT, w_r, w_i, gw, x, (__nv_bfloat16*)d_out, mp);
}
```

```cpp
#include <cuda_runtime.h>
#include <cuda_bf16.h>
#include <cuda.h>
#include <stdint.h>

namespace tbl {
constexpr double PI = 3.14159265358979323846264338327950288;
constexpr double sin_s(double x) { double t = x, s = x; for (int n = 1; n < 12; n++) { t *= -x * x / ((2 * n) * (2 * n + 1)); s += t; } return s; }
constexpr double cos_s(double x) { double t = 1, s = 1; for (int n = 1; n < 12; n++) { t *= -x * x / ((2 * n - 1) * (2 * n)); s += t; } return s; }
constexpr double cos2048(int m) {
  m &= 2047; if (m > 1024) m = 2048 - m;
  bool neg = false; if (m > 512) { m = 1024 - m; neg = true; }
  double v = (m <= 256) ? cos_s(2 * PI * m / 2048) : sin_s(2 * PI * (512 - m) / 2048);
  return neg ? -v : v;
}
constexpr uint16_t to_bf16(double v) {
  if (v == 0) return 0;
  uint16_t s = 0; if (v < 0) { s = 0x8000; v = -v; }
  int e = 0; while (v >= 2) { v /= 2; e++; } while (v < 1) { v *= 2; e--; }
  double m = (v - 1) * 128; int mi = (int)m; double fr = m - mi;
  if (fr > 0.5 || (fr == 0.5 && (mi & 1))) mi++;
  if (mi == 128) { mi = 0; e++; }
  return (uint16_t)(s | ((e + 127) << 7) | mi);
}
struct CosT { uint16_t v[2048]; constexpr CosT() : v() { for (int i = 0; i < 2048; i++) v[i] = to_bf16(cos2048(i)); } };
struct alignas(1024) FT {
  uint16_t v[512 * 512];
  constexpr FT() : v() {
    CosT c;
    for (int r = 0; r < 512; r++) {
      int k = (r >> 4) * 8 + (r & 7), e = (r >> 3) & 1;
      int mul = 4 * k, add = e ? 512 : 0;
      if (k == 0 && e == 1) { mul = 1024; add = 0; }
      for (int d = 0; d < 512; d++) v[r * 512 + d] = c.v[(d * mul + add) & 2047];
    }
  }
};
struct alignas(1024) ET {
  uint16_t v[2048 * 128];
  constexpr ET() : v() {
    CosT c;
    for (int s = 0; s < 2048; s++)
      for (int j = 0; j < 64; j++) {
        const int o = (s & 31) * 8192 + (s >> 5) * 64 + j;
        v[o] = c.v[(s * j) & 2047]; v[o + 4096] = c.v[(s * j + 512) & 2047];
      }
  }
};
struct alignas(1024) DT {
  uint16_t v[64 * 64];
  constexpr DT() : v() {
    CosT c;
    for (int r = 0; r < 64; r++)
      for (int n = 0; n < 64; n++) {
        const int sg = r >> 1, s0 = (sg & ~6) | ((sg & 2) << 1) | ((sg & 4) >> 1), e = r & 1, f = n & 1;
        const int m = 64 * s0 * (n >> 1) + (e == f ? 0 : e ? -512 : 512);
        v[r * 64 + (((n >> 3) ^ (r & 7)) << 3) + (n & 7)] = c.v[m & 2047];
      }
  }
};
}

__device__ constexpr tbl::FT g_FT = tbl::FT();
__device__ constexpr tbl::ET g_ET = tbl::ET();
__device__ constexpr tbl::DT g_DT = tbl::DT();

struct alignas(1024) Work {
  unsigned epoch[132 * 8];
  unsigned cntX[8 * 32], cntT[8 * 32], cntP[128 * 32], cntW[32], cntH[32];
  alignas(16) float gate[16 * 128];
  alignas(16) uint2 Wh[2 * 2048];
  alignas(16) uint2 Ts[32 * 64];
  alignas(1024) uint16_t X[129 * 8192];
  alignas(1024) uint16_t T[32 * 64 * 512];
  alignas(1024) uint4 part[128 * 3 * 1024];
};
__device__ Work g_work;
#define PROF_EV(i) do {} while (0)
#define PROF_CK(i) do {} while (0)

__device__ __forceinline__ uint32_t smem_u32(const void* p) { return (uint32_t)__cvta_generic_to_shared(p); }
__device__ __forceinline__ void mbar_init(uint32_t bar, uint32_t cnt) { asm volatile("mbarrier.init.shared::cta.b64 [%0], %1;" ::"r"(bar), "r"(cnt)); }
__device__ __forceinline__ void mbar_expect_tx(uint32_t bar, uint32_t bytes) { asm volatile("mbarrier.arrive.expect_tx.shared::cta.b64 _, [%0], %1;" ::"r"(bar), "r"(bytes) : "memory"); }
__device__ __forceinline__ void mbar_arrive(uint32_t bar) { asm volatile("mbarrier.arrive.shared::cta.b64 _, [%0];" ::"r"(bar) : "memory"); }
__device__ __forceinline__ bool elect_one() {
  uint32_t p;
  asm volatile("{\n.reg .pred p;\nelect.sync _|p, 0xffffffff;\nselp.u32 %0, 1, 0, p;\n}" : "=r"(p));
  return p;
}
__device__ __forceinline__ void mbar_arrive_if(bool p, uint32_t bar) {
  asm volatile("{\n.reg .pred p;\nsetp.ne.b32 p, %1, 0;\n@p mbarrier.arrive.shared::cta.b64 _, [%0];\n}" ::"r"(bar), "r"((int)p) : "memory");
}
__device__ __forceinline__ void hint_add_if(bool p, unsigned* a) {
  asm volatile("{\n.reg .pred p;\nsetp.ne.b32 p, %1, 0;\n@p red.relaxed.gpu.global.add.u32 [%0], 1;\n}" ::"l"(a), "r"((int)p) : "memory");
}
__device__ __forceinline__ bool mbar_try(uint32_t bar, uint32_t parity) {
  uint32_t ok;
  asm volatile("{\n.reg .pred p;\nmbarrier.test_wait.parity.shared::cta.b64 p, [%1], %2;\nselp.u32 %0, 1, 0, p;\n}" : "=r"(ok) : "r"(bar), "r"(parity) : "memory");
  return ok;
}
__device__ __forceinline__ void mbar_wait(uint32_t bar, uint32_t parity) {
  asm volatile(
      "{\n.reg .pred p;\n.reg .u32 n;\nmov.u32 n, 0;\n"
      "W_LOOP:\nmbarrier.try_wait.parity.shared::cta.b64 p, [%0], %1;\n@p bra W_DONE;\n"
      "add.u32 n, n, 1;\nsetp.lt.u32 p, n, 0x40000;\n@p bra W_LOOP;\ntrap;\nW_DONE:\n}" ::"r"(bar), "r"(parity) : "memory");
}
__device__ __forceinline__ void bulk_load(uint32_t dst, const void* src, uint32_t bytes, uint32_t bar) {
  asm volatile("cp.async.bulk.shared::cluster.global.mbarrier::complete_tx::bytes [%0], [%1], %2, [%3];" ::"r"(dst), "l"(src), "r"(bytes), "r"(bar) : "memory");
}
__device__ __forceinline__ void spin_guard(uint32_t t0) { if ((uint32_t)clock() - t0 > (1u << 30)) __trap(); }
__device__ __forceinline__ float2 ld_x2(const float2* p) { float2 v; asm volatile("ld.relaxed.gpu.global.v2.f32 {%0,%1}, [%2];" : "=f"(v.x), "=f"(v.y) : "l"(p) : "memory"); return v; }
__device__ __forceinline__ void st_u2(uint2* p, uint32_t a, uint32_t b) { asm volatile("st.relaxed.gpu.global.v2.u32 [%0], {%1,%2};" ::"l"(p), "r"(a), "r"(b) : "memory"); }
__device__ __forceinline__ uint32_t ld_x1(const void* p) { uint32_t v; asm volatile("ld.relaxed.gpu.global.u32 %0, [%1];" : "=r"(v) : "l"(p) : "memory"); return v; }
__device__ __forceinline__ uint4 ld_x4(const void* p) { uint4 v; asm volatile("ld.relaxed.gpu.global.v4.u32 {%0,%1,%2,%3}, [%4];" : "=r"(v.x), "=r"(v.y), "=r"(v.z), "=r"(v.w) : "l"(p) : "memory"); return v; }
__device__ __forceinline__ uint32_t mapa(uint32_t a, uint32_t cta) { uint32_t r; asm volatile("mapa.shared::cluster.u32 %0, %1, %2;" : "=r"(r) : "r"(a), "r"(cta)); return r; }
__device__ __forceinline__ void stsm4t(uint32_t a, uint32_t r0, uint32_t r1, uint32_t r2, uint32_t r3) {
  asm volatile("stmatrix.sync.aligned.m8n8.x4.trans.shared.b16 [%0], {%1,%2,%3,%4};" ::"r"(a), "r"(r0), "r"(r1), "r"(r2), "r"(r3) : "memory");
}
__device__ __forceinline__ void hint_add(unsigned* p) { asm volatile("red.relaxed.gpu.global.add.u32 [%0], 1;" ::"l"(p) : "memory"); }
__device__ __forceinline__ void hint_wait(const unsigned* p, unsigned target) {
  const uint32_t t0 = (uint32_t)clock();
  while ((int)(ld_x1(p) - target) < 0) spin_guard(t0);
}
__device__ __forceinline__ void bulk_done_signal(unsigned* p) {
  asm volatile("cp.async.bulk.commit_group;\ncp.async.bulk.wait_group 0;\nfence.proxy.async.global;" ::: "memory");
  hint_add(p);
}
__device__ __forceinline__ void flag_wait(const unsigned* p, unsigned target) {
  hint_wait(p, target);
  asm volatile("fence.proxy.async.global;" ::: "memory");
}
__device__ __forceinline__ void tma2d(uint32_t dst, const CUtensorMap* m, uint32_t bar, int c0, int c1) {
  asm volatile("cp.async.bulk.tensor.2d.shared::cluster.global.mbarrier::complete_tx::bytes [%0], [%1, {%3, %4}], [%2];" ::"r"(dst), "l"(m), "r"(bar), "r"(c0), "r"(c1) : "memory");
}
__device__ __forceinline__ void tma3d(uint32_t dst, const CUtensorMap* m, uint32_t bar, int c0, int c1, int c2) {
  asm volatile("cp.async.bulk.tensor.3d.shared::cluster.global.mbarrier::complete_tx::bytes [%0], [%1, {%3, %4, %5}], [%2];" ::"r"(dst), "l"(m), "r"(bar), "r"(c0), "r"(c1), "r"(c2) : "memory");
}
__device__ __forceinline__ void tma4d(uint32_t dst, const CUtensorMap* m, uint32_t bar, int c0, int c1, int c2, int c3) {
  asm volatile("cp.async.bulk.tensor.4d.shared::cluster.global.mbarrier::complete_tx::bytes [%0], [%1, {%3, %4, %5, %6}], [%2];" ::"r"(dst), "l"(m), "r"(bar), "r"(c0), "r"(c1), "r"(c2), "r"(c3) : "memory");
}
__device__ __forceinline__ void wg_fence() { asm volatile("wgmma.fence.sync.aligned;" ::: "memory"); }
__device__ __forceinline__ void wg_commit() { asm volatile("wgmma.commit_group.sync.aligned;" ::: "memory"); }
template <int N> __device__ __forceinline__ void wg_wait() { asm volatile("wgmma.wait_group.sync.aligned %0;" ::"n"(N) : "memory"); }
template <int O, int N, int NN> __device__ __forceinline__ void fence_regs(float (&d)[NN]) {
#pragma unroll
  for (int i = 0; i < N; i++) asm volatile("" : "+f"(d[O + i])::"memory");
}
__device__ __forceinline__ uint32_t pack_bf16(float lo, float hi) {
  uint32_t r; asm("cvt.rn.bf16x2.f32 %0, %1, %2;" : "=r"(r) : "f"(hi), "f"(lo)); return r;
}
__device__ __forceinline__ uint32_t pack_pin(float lo, float hi) {
  uint32_t r; asm volatile("cvt.rn.bf16x2.f32 %0, %1, %2;" : "=r"(r) : "f"(hi), "f"(lo) : "memory"); return r;
}
__device__ __forceinline__ uint32_t add_bf2(uint32_t a, uint32_t b) { uint32_t r; asm("add.rn.bf16x2 %0, %1, %2;" : "=r"(r) : "r"(a), "r"(b)); return r; }
__device__ __forceinline__ float bf_lo(uint32_t u) { return __uint_as_float(u << 16); }
__device__ __forceinline__ float bf_hi(uint32_t u) { return __uint_as_float(u & 0xffff0000u); }

__device__ __forceinline__ uint64_t d128(uint32_t lo) { uint64_t d; asm("mov.b64 %0, {%1, 0x40000040};" : "=l"(d) : "r"(lo)); return d; }
__device__ __forceinline__ uint64_t d64(uint32_t lo) { uint64_t d; asm("mov.b64 %0, {%1, 0x80000020};" : "=l"(d) : "r"(lo)); return d; }
template<int O,int TB,int ACC,int NN> __device__ __forceinline__ void mma_ss64(float (&d)[NN], uint64_t da, uint64_t db, int sd = 0){
  if constexpr (ACC == 1) asm volatile("wgmma.mma_async.sync.aligned.m64n64k16.f32.bf16.bf16 {%0,%1,%2,%3,%4,%5,%6,%7,%8,%9,%10,%11,%12,%13,%14,%15,%16,%17,%18,%19,%20,%21,%22,%23,%24,%25,%26,%27,%28,%29,%30,%31}, %32, %33, 1, 1, 1, %35, %34;"
   : "+f"(d[O+0]), "+f"(d[O+1]), "+f"(d[O+2]), "+f"(d[O+3]), "+f"(d[O+4]), "+f"(d[O+5]), "+f"(d[O+6]), "+f"(d[O+7]), "+f"(d[O+8]), "+f"(d[O+9]), "+f"(d[O+10]), "+f"(d[O+11]), "+f"(d[O+12]), "+f"(d[O+13]), "+f"(d[O+14]), "+f"(d[O+15]), "+f"(d[O+16]), "+f"(d[O+17]), "+f"(d[O+18]), "+f"(d[O+19]), "+f"(d[O+20]), "+f"(d[O+21]), "+f"(d[O+22]), "+f"(d[O+23]), "+f"(d[O+24]), "+f"(d[O+25]), "+f"(d[O+26]), "+f"(d[O+27]), "+f"(d[O+28]), "+f"(d[O+29]), "+f"(d[O+30]), "+f"(d[O+31])
   : "l"(da), "l"(db), "n"(TB & 1), "n"(TB >> 1));
  else if constexpr (ACC == 0) asm volatile("wgmma.mma_async.sync.aligned.m64n64k16.f32.bf16.bf16 {%0,%1,%2,%3,%4,%5,%6,%7,%8,%9,%10,%11,%12,%13,%14,%15,%16,%17,%18,%19,%20,%21,%22,%23,%24,%25,%26,%27,%28,%29,%30,%31}, %32, %33, 0, 1, 1, %35, %34;"
   : "=f"(d[O+0]), "=f"(d[O+1]), "=f"(d[O+2]), "=f"(d[O+3]), "=f"(d[O+4]), "=f"(d[O+5]), "=f"(d[O+6]), "=f"(d[O+7]), "=f"(d[O+8]), "=f"(d[O+9]), "=f"(d[O+10]), "=f"(d[O+11]), "=f"(d[O+12]), "=f"(d[O+13]), "=f"(d[O+14]), "=f"(d[O+15]), "=f"(d[O+16]), "=f"(d[O+17]), "=f"(d[O+18]), "=f"(d[O+19]), "=f"(d[O+20]), "=f"(d[O+21]), "=f"(d[O+22]), "=f"(d[O+23]), "=f"(d[O+24]), "=f"(d[O+25]), "=f"(d[O+26]), "=f"(d[O+27]), "=f"(d[O+28]), "=f"(d[O+29]), "=f"(d[O+30]), "=f"(d[O+31])
   : "l"(da), "l"(db), "n"(TB & 1), "n"(TB >> 1));
  else asm volatile("{\n.reg .pred p;\nsetp.ne.b32 p, %36, 0;\nwgmma.mma_async.sync.aligned.m64n64k16.f32.bf16.bf16 {%0,%1,%2,%3,%4,%5,%6,%7,%8,%9,%10,%11,%12,%13,%14,%15,%16,%17,%18,%19,%20,%21,%22,%23,%24,%25,%26,%27,%28,%29,%30,%31}, %32, %33, p, 1, 1, %35, %34;\n}"
   : "+f"(d[O+0]), "+f"(d[O+1]), "+f"(d[O+2]), "+f"(d[O+3]), "+f"(d[O+4]), "+f"(d[O+5]), "+f"(d[O+6]), "+f"(d[O+7]), "+f"(d[O+8]), "+f"(d[O+9]), "+f"(d[O+10]), "+f"(d[O+11]), "+f"(d[O+12]), "+f"(d[O+13]), "+f"(d[O+14]), "+f"(d[O+15]), "+f"(d[O+16]), "+f"(d[O+17]), "+f"(d[O+18]), "+f"(d[O+19]), "+f"(d[O+20]), "+f"(d[O+21]), "+f"(d[O+22]), "+f"(d[O+23]), "+f"(d[O+24]), "+f"(d[O+25]), "+f"(d[O+26]), "+f"(d[O+27]), "+f"(d[O+28]), "+f"(d[O+29]), "+f"(d[O+30]), "+f"(d[O+31])
   : "l"(da), "l"(db), "n"(TB & 1), "n"(TB >> 1), "r"(sd));
}
template<int O,int TB,int ACC,int NN> __device__ __forceinline__ void mma_rs64(float (&d)[NN], uint32_t a0, uint32_t a1, uint32_t a2, uint32_t a3, uint64_t db, int sd = 0){
  if constexpr (ACC == 1) asm volatile("wgmma.mma_async.sync.aligned.m64n64k16.f32.bf16.bf16 {%0,%1,%2,%3,%4,%5,%6,%7,%8,%9,%10,%11,%12,%13,%14,%15,%16,%17,%18,%19,%20,%21,%22,%23,%24,%25,%26,%27,%28,%29,%30,%31}, {%32,%33,%34,%35}, %36, 1, 1, 1, %37;"
   : "+f"(d[O+0]), "+f"(d[O+1]), "+f"(d[O+2]), "+f"(d[O+3]), "+f"(d[O+4]), "+f"(d[O+5]), "+f"(d[O+6]), "+f"(d[O+7]), "+f"(d[O+8]), "+f"(d[O+9]), "+f"(d[O+10]), "+f"(d[O+11]), "+f"(d[O+12]), "+f"(d[O+13]), "+f"(d[O+14]), "+f"(d[O+15]), "+f"(d[O+16]), "+f"(d[O+17]), "+f"(d[O+18]), "+f"(d[O+19]), "+f"(d[O+20]), "+f"(d[O+21]), "+f"(d[O+22]), "+f"(d[O+23]), "+f"(d[O+24]), "+f"(d[O+25]), "+f"(d[O+26]), "+f"(d[O+27]), "+f"(d[O+28]), "+f"(d[O+29]), "+f"(d[O+30]), "+f"(d[O+31])
   : "r"(a0), "r"(a1), "r"(a2), "r"(a3), "l"(db), "n"(TB));
  else if constexpr (ACC == 0) asm volatile("wgmma.mma_async.sync.aligned.m64n64k16.f32.bf16.bf16 {%0,%1,%2,%3,%4,%5,%6,%7,%8,%9,%10,%11,%12,%13,%14,%15,%16,%17,%18,%19,%20,%21,%22,%23,%24,%25,%26,%27,%28,%29,%30,%31}, {%32,%33,%34,%35}, %36, 0, 1, 1, %37;"
   : "=f"(d[O+0]), "=f"(d[O+1]), "=f"(d[O+2]), "=f"(d[O+3]), "=f"(d[O+4]), "=f"(d[O+5]), "=f"(d[O+6]), "=f"(d[O+7]), "=f"(d[O+8]), "=f"(d[O+9]), "=f"(d[O+10]), "=f"(d[O+11]), "=f"(d[O+12]), "=f"(d[O+13]), "=f"(d[O+14]), "=f"(d[O+15]), "=f"(d[O+16]), "=f"(d[O+17]), "=f"(d[O+18]), "=f"(d[O+19]), "=f"(d[O+20]), "=f"(d[O+21]), "=f"(d[O+22]), "=f"(d[O+23]), "=f"(d[O+24]), "=f"(d[O+25]), "=f"(d[O+26]), "=f"(d[O+27]), "=f"(d[O+28]), "=f"(d[O+29]), "=f"(d[O+30]), "=f"(d[O+31])
   : "r"(a0), "r"(a1), "r"(a2), "r"(a3), "l"(db), "n"(TB));
  else asm volatile("{\n.reg .pred p;\nsetp.ne.b32 p, %38, 0;\nwgmma.mma_async.sync.aligned.m64n64k16.f32.bf16.bf16 {%0,%1,%2,%3,%4,%5,%6,%7,%8,%9,%10,%11,%12,%13,%14,%15,%16,%17,%18,%19,%20,%21,%22,%23,%24,%25,%26,%27,%28,%29,%30,%31}, {%32,%33,%34,%35}, %36, p, 1, 1, %37;\n}"
   : "+f"(d[O+0]), "+f"(d[O+1]), "+f"(d[O+2]), "+f"(d[O+3]), "+f"(d[O+4]), "+f"(d[O+5]), "+f"(d[O+6]), "+f"(d[O+7]), "+f"(d[O+8]), "+f"(d[O+9]), "+f"(d[O+10]), "+f"(d[O+11]), "+f"(d[O+12]), "+f"(d[O+13]), "+f"(d[O+14]), "+f"(d[O+15]), "+f"(d[O+16]), "+f"(d[O+17]), "+f"(d[O+18]), "+f"(d[O+19]), "+f"(d[O+20]), "+f"(d[O+21]), "+f"(d[O+22]), "+f"(d[O+23]), "+f"(d[O+24]), "+f"(d[O+25]), "+f"(d[O+26]), "+f"(d[O+27]), "+f"(d[O+28]), "+f"(d[O+29]), "+f"(d[O+30]), "+f"(d[O+31])
   : "r"(a0), "r"(a1), "r"(a2), "r"(a3), "l"(db), "n"(TB), "r"(sd));
}
template<int O,int TB,int ACC,int NN> __device__ __forceinline__ void mma_ss128(float (&d)[NN], uint64_t da, uint64_t db, int sd = 0){
  if constexpr (ACC == 1) asm volatile("wgmma.mma_async.sync.aligned.m64n128k16.f32.bf16.bf16 {%0,%1,%2,%3,%4,%5,%6,%7,%8,%9,%10,%11,%12,%13,%14,%15,%16,%17,%18,%19,%20,%21,%22,%23,%24,%25,%26,%27,%28,%29,%30,%31,%32,%33,%34,%35,%36,%37,%38,%39,%40,%41,%42,%43,%44,%45,%46,%47,%48,%49,%50,%51,%52,%53,%54,%55,%56,%57,%58,%59,%60,%61,%62,%63}, %64, %65, 1, 1, 1, %67, %66;"
   : "+f"(d[O+0]), "+f"(d[O+1]), "+f"(d[O+2]), "+f"(d[O+3]), "+f"(d[O+4]), "+f"(d[O+5]), "+f"(d[O+6]), "+f"(d[O+7]), "+f"(d[O+8]), "+f"(d[O+9]), "+f"(d[O+10]), "+f"(d[O+11]), "+f"(d[O+12]), "+f"(d[O+13]), "+f"(d[O+14]), "+f"(d[O+15]), "+f"(d[O+16]), "+f"(d[O+17]), "+f"(d[O+18]), "+f"(d[O+19]), "+f"(d[O+20]), "+f"(d[O+21]), "+f"(d[O+22]), "+f"(d[O+23]), "+f"(d[O+24]), "+f"(d[O+25]), "+f"(d[O+26]), "+f"(d[O+27]), "+f"(d[O+28]), "+f"(d[O+29]), "+f"(d[O+30]), "+f"(d[O+31]), "+f"(d[O+32]), "+f"(d[O+33]), "+f"(d[O+34]), "+f"(d[O+35]), "+f"(d[O+36]), "+f"(d[O+37]), "+f"(d[O+38]), "+f"(d[O+39]), "+f"(d[O+40]), "+f"(d[O+41]), "+f"(d[O+42]), "+f"(d[O+43]), "+f"(d[O+44]), "+f"(d[O+45]), "+f"(d[O+46]), "+f"(d[O+47]), "+f"(d[O+48]), "+f"(d[O+49]), "+f"(d[O+50]), "+f"(d[O+51]), "+f"(d[O+52]), "+f"(d[O+53]), "+f"(d[O+54]), "+f"(d[O+55]), "+f"(d[O+56]), "+f"(d[O+57]), "+f"(d[O+58]), "+f"(d[O+59]), "+f"(d[O+60]), "+f"(d[O+61]), "+f"(d[O+62]), "+f"(d[O+63])
   : "l"(da), "l"(db), "n"(TB & 1), "n"(TB >> 1));
  else if constexpr (ACC == 0) asm volatile("wgmma.mma_async.sync.aligned.m64n128k16.f32.bf16.bf16 {%0,%1,%2,%3,%4,%5,%6,%7,%8,%9,%10,%11,%12,%13,%14,%15,%16,%17,%18,%19,%20,%21,%22,%23,%24,%25,%26,%27,%28,%29,%30,%31,%32,%33,%34,%35,%36,%37,%38,%39,%40,%41,%42,%43,%44,%45,%46,%47,%48,%49,%50,%51,%52,%53,%54,%55,%56,%57,%58,%59,%60,%61,%62,%63}, %64, %65, 0, 1, 1, %67, %66;"
   : "=f"(d[O+0]), "=f"(d[O+1]), "=f"(d[O+2]), "=f"(d[O+3]), "=f"(d[O+4]), "=f"(d[O+5]), "=f"(d[O+6]), "=f"(d[O+7]), "=f"(d[O+8]), "=f"(d[O+9]), "=f"(d[O+10]), "=f"(d[O+11]), "=f"(d[O+12]), "=f"(d[O+13]), "=f"(d[O+14]), "=f"(d[O+15]), "=f"(d[O+16]), "=f"(d[O+17]), "=f"(d[O+18]), "=f"(d[O+19]), "=f"(d[O+20]), "=f"(d[O+21]), "=f"(d[O+22]), "=f"(d[O+23]), "=f"(d[O+24]), "=f"(d[O+25]), "=f"(d[O+26]), "=f"(d[O+27]), "=f"(d[O+28]), "=f"(d[O+29]), "=f"(d[O+30]), "=f"(d[O+31]), "=f"(d[O+32]), "=f"(d[O+33]), "=f"(d[O+34]), "=f"(d[O+35]), "=f"(d[O+36]), "=f"(d[O+37]), "=f"(d[O+38]), "=f"(d[O+39]), "=f"(d[O+40]), "=f"(d[O+41]), "=f"(d[O+42]), "=f"(d[O+43]), "=f"(d[O+44]), "=f"(d[O+45]), "=f"(d[O+46]), "=f"(d[O+47]), "=f"(d[O+48]), "=f"(d[O+49]), "=f"(d[O+50]), "=f"(d[O+51]), "=f"(d[O+52]), "=f"(d[O+53]), "=f"(d[O+54]), "=f"(d[O+55]), "=f"(d[O+56]), "=f"(d[O+57]), "=f"(d[O+58]), "=f"(d[O+59]), "=f"(d[O+60]), "=f"(d[O+61]), "=f"(d[O+62]), "=f"(d[O+63])
   : "l"(da), "l"(db), "n"(TB & 1), "n"(TB >> 1));
  else asm volatile("{\n.reg .pred p;\nsetp.ne.b32 p, %68, 0;\nwgmma.mma_async.sync.aligned.m64n128k16.f32.bf16.bf16 {%0,%1,%2,%3,%4,%5,%6,%7,%8,%9,%10,%11,%12,%13,%14,%15,%16,%17,%18,%19,%20,%21,%22,%23,%24,%25,%26,%27,%28,%29,%30,%31,%32,%33,%34,%35,%36,%37,%38,%39,%40,%41,%42,%43,%44,%45,%46,%47,%48,%49,%50,%51,%52,%53,%54,%55,%56,%57,%58,%59,%60,%61,%62,%63}, %64, %65, p, 1, 1, %67, %66;\n}"
   : "+f"(d[O+0]), "+f"(d[O+1]), "+f"(d[O+2]), "+f"(d[O+3]), "+f"(d[O+4]), "+f"(d[O+5]), "+f"(d[O+6]), "+f"(d[O+7]), "+f"(d[O+8]), "+f"(d[O+9]), "+f"(d[O+10]), "+f"(d[O+11]), "+f"(d[O+12]), "+f"(d[O+13]), "+f"(d[O+14]), "+f"(d[O+15]), "+f"(d[O+16]), "+f"(d[O+17]), "+f"(d[O+18]), "+f"(d[O+19]), "+f"(d[O+20]), "+f"(d[O+21]), "+f"(d[O+22]), "+f"(d[O+23]), "+f"(d[O+24]), "+f"(d[O+25]), "+f"(d[O+26]), "+f"(d[O+27]), "+f"(d[O+28]), "+f"(d[O+29]), "+f"(d[O+30]), "+f"(d[O+31]), "+f"(d[O+32]), "+f"(d[O+33]), "+f"(d[O+34]), "+f"(d[O+35]), "+f"(d[O+36]), "+f"(d[O+37]), "+f"(d[O+38]), "+f"(d[O+39]), "+f"(d[O+40]), "+f"(d[O+41]), "+f"(d[O+42]), "+f"(d[O+43]), "+f"(d[O+44]), "+f"(d[O+45]), "+f"(d[O+46]), "+f"(d[O+47]), "+f"(d[O+48]), "+f"(d[O+49]), "+f"(d[O+50]), "+f"(d[O+51]), "+f"(d[O+52]), "+f"(d[O+53]), "+f"(d[O+54]), "+f"(d[O+55]), "+f"(d[O+56]), "+f"(d[O+57]), "+f"(d[O+58]), "+f"(d[O+59]), "+f"(d[O+60]), "+f"(d[O+61]), "+f"(d[O+62]), "+f"(d[O+63])
   : "l"(da), "l"(db), "n"(TB & 1), "n"(TB >> 1), "r"(sd));
}
template<int O,int TB,int ACC,int NN> __device__ __forceinline__ void mma_rs128(float (&d)[NN], uint32_t a0, uint32_t a1, uint32_t a2, uint32_t a3, uint64_t db, int sd = 0){
  if constexpr (ACC == 1) asm volatile("wgmma.mma_async.sync.aligned.m64n128k16.f32.bf16.bf16 {%0,%1,%2,%3,%4,%5,%6,%7,%8,%9,%10,%11,%12,%13,%14,%15,%16,%17,%18,%19,%20,%21,%22,%23,%24,%25,%26,%27,%28,%29,%30,%31,%32,%33,%34,%35,%36,%37,%38,%39,%40,%41,%42,%43,%44,%45,%46,%47,%48,%49,%50,%51,%52,%53,%54,%55,%56,%57,%58,%59,%60,%61,%62,%63}, {%64,%65,%66,%67}, %68, 1, 1, 1, %69;"
   : "+f"(d[O+0]), "+f"(d[O+1]), "+f"(d[O+2]), "+f"(d[O+3]), "+f"(d[O+4]), "+f"(d[O+5]), "+f"(d[O+6]), "+f"(d[O+7]), "+f"(d[O+8]), "+f"(d[O+9]), "+f"(d[O+10]), "+f"(d[O+11]), "+f"(d[O+12]), "+f"(d[O+13]), "+f"(d[O+14]), "+f"(d[O+15]), "+f"(d[O+16]), "+f"(d[O+17]), "+f"(d[O+18]), "+f"(d[O+19]), "+f"(d[O+20]), "+f"(d[O+21]), "+f"(d[O+22]), "+f"(d[O+23]), "+f"(d[O+24]), "+f"(d[O+25]), "+f"(d[O+26]), "+f"(d[O+27]), "+f"(d[O+28]), "+f"(d[O+29]), "+f"(d[O+30]), "+f"(d[O+31]), "+f"(d[O+32]), "+f"(d[O+33]), "+f"(d[O+34]), "+f"(d[O+35]), "+f"(d[O+36]), "+f"(d[O+37]), "+f"(d[O+38]), "+f"(d[O+39]), "+f"(d[O+40]), "+f"(d[O+41]), "+f"(d[O+42]), "+f"(d[O+43]), "+f"(d[O+44]), "+f"(d[O+45]), "+f"(d[O+46]), "+f"(d[O+47]), "+f"(d[O+48]), "+f"(d[O+49]), "+f"(d[O+50]), "+f"(d[O+51]), "+f"(d[O+52]), "+f"(d[O+53]), "+f"(d[O+54]), "+f"(d[O+55]), "+f"(d[O+56]), "+f"(d[O+57]), "+f"(d[O+58]), "+f"(d[O+59]), "+f"(d[O+60]), "+f"(d[O+61]), "+f"(d[O+62]), "+f"(d[O+63])
   : "r"(a0), "r"(a1), "r"(a2), "r"(a3), "l"(db), "n"(TB));
  else if constexpr (ACC == 0) asm volatile("wgmma.mma_async.sync.aligned.m64n128k16.f32.bf16.bf16 {%0,%1,%2,%3,%4,%5,%6,%7,%8,%9,%10,%11,%12,%13,%14,%15,%16,%17,%18,%19,%20,%21,%22,%23,%24,%25,%26,%27,%28,%29,%30,%31,%32,%33,%34,%35,%36,%37,%38,%39,%40,%41,%42,%43,%44,%45,%46,%47,%48,%49,%50,%51,%52,%53,%54,%55,%56,%57,%58,%59,%60,%61,%62,%63}, {%64,%65,%66,%67}, %68, 0, 1, 1, %69;"
   : "=f"(d[O+0]), "=f"(d[O+1]), "=f"(d[O+2]), "=f"(d[O+3]), "=f"(d[O+4]), "=f"(d[O+5]), "=f"(d[O+6]), "=f"(d[O+7]), "=f"(d[O+8]), "=f"(d[O+9]), "=f"(d[O+10]), "=f"(d[O+11]), "=f"(d[O+12]), "=f"(d[O+13]), "=f"(d[O+14]), "=f"(d[O+15]), "=f"(d[O+16]), "=f"(d[O+17]), "=f"(d[O+18]), "=f"(d[O+19]), "=f"(d[O+20]), "=f"(d[O+21]), "=f"(d[O+22]), "=f"(d[O+23]), "=f"(d[O+24]), "=f"(d[O+25]), "=f"(d[O+26]), "=f"(d[O+27]), "=f"(d[O+28]), "=f"(d[O+29]), "=f"(d[O+30]), "=f"(d[O+31]), "=f"(d[O+32]), "=f"(d[O+33]), "=f"(d[O+34]), "=f"(d[O+35]), "=f"(d[O+36]), "=f"(d[O+37]), "=f"(d[O+38]), "=f"(d[O+39]), "=f"(d[O+40]), "=f"(d[O+41]), "=f"(d[O+42]), "=f"(d[O+43]), "=f"(d[O+44]), "=f"(d[O+45]), "=f"(d[O+46]), "=f"(d[O+47]), "=f"(d[O+48]), "=f"(d[O+49]), "=f"(d[O+50]), "=f"(d[O+51]), "=f"(d[O+52]), "=f"(d[O+53]), "=f"(d[O+54]), "=f"(d[O+55]), "=f"(d[O+56]), "=f"(d[O+57]), "=f"(d[O+58]), "=f"(d[O+59]), "=f"(d[O+60]), "=f"(d[O+61]), "=f"(d[O+62]), "=f"(d[O+63])
   : "r"(a0), "r"(a1), "r"(a2), "r"(a3), "l"(db), "n"(TB));
  else asm volatile("{\n.reg .pred p;\nsetp.ne.b32 p, %70, 0;\nwgmma.mma_async.sync.aligned.m64n128k16.f32.bf16.bf16 {%0,%1,%2,%3,%4,%5,%6,%7,%8,%9,%10,%11,%12,%13,%14,%15,%16,%17,%18,%19,%20,%21,%22,%23,%24,%25,%26,%27,%28,%29,%30,%31,%32,%33,%34,%35,%36,%37,%38,%39,%40,%41,%42,%43,%44,%45,%46,%47,%48,%49,%50,%51,%52,%53,%54,%55,%56,%57,%58,%59,%60,%61,%62,%63}, {%64,%65,%66,%67}, %68, p, 1, 1, %69;\n}"
   : "+f"(d[O+0]), "+f"(d[O+1]), "+f"(d[O+2]), "+f"(d[O+3]), "+f"(d[O+4]), "+f"(d[O+5]), "+f"(d[O+6]), "+f"(d[O+7]), "+f"(d[O+8]), "+f"(d[O+9]), "+f"(d[O+10]), "+f"(d[O+11]), "+f"(d[O+12]), "+f"(d[O+13]), "+f"(d[O+14]), "+f"(d[O+15]), "+f"(d[O+16]), "+f"(d[O+17]), "+f"(d[O+18]), "+f"(d[O+19]), "+f"(d[O+20]), "+f"(d[O+21]), "+f"(d[O+22]), "+f"(d[O+23]), "+f"(d[O+24]), "+f"(d[O+25]), "+f"(d[O+26]), "+f"(d[O+27]), "+f"(d[O+28]), "+f"(d[O+29]), "+f"(d[O+30]), "+f"(d[O+31]), "+f"(d[O+32]), "+f"(d[O+33]), "+f"(d[O+34]), "+f"(d[O+35]), "+f"(d[O+36]), "+f"(d[O+37]), "+f"(d[O+38]), "+f"(d[O+39]), "+f"(d[O+40]), "+f"(d[O+41]), "+f"(d[O+42]), "+f"(d[O+43]), "+f"(d[O+44]), "+f"(d[O+45]), "+f"(d[O+46]), "+f"(d[O+47]), "+f"(d[O+48]), "+f"(d[O+49]), "+f"(d[O+50]), "+f"(d[O+51]), "+f"(d[O+52]), "+f"(d[O+53]), "+f"(d[O+54]), "+f"(d[O+55]), "+f"(d[O+56]), "+f"(d[O+57]), "+f"(d[O+58]), "+f"(d[O+59]), "+f"(d[O+60]), "+f"(d[O+61]), "+f"(d[O+62]), "+f"(d[O+63])
   : "r"(a0), "r"(a1), "r"(a2), "r"(a3), "l"(db), "n"(TB), "r"(sd));
}

#define NEARLY 0
#define XAHEAD 3
#define HEADN 6
#define WBATCH 1
#define WB 8
#define WSLEEP 20
#define XSPREAD 4
#define NOSEND 0
#define MSPLIT 2
#define PFALL 1
#define L2PF 0
#define STAG 0
#define EPF 2
#define XNB 2
#define FNB 0
#define GNB 0
#define TH 4
#define PF0 4
#define FSPLIT 1
#define MGLU 1
#define SPC 2
#define TL 14
#define GKB 4
#define T0A 8
#define TGATE 1
#define FIN32 1
#define SPACE 100
#define WPF 1
#define WAFTER 7
#define WPACE 0
#define GATE_AT 4
#define TPACE 40
#define PFMODE 0
#define MAPMODE 1
template <int V> struct IC { static constexpr int value = V; };
struct Maps { CUtensorMap x, ft, g64, u64, e, wr, wi, xs, ts, t, g32, u32, d224; };

constexpr int NCTA = 130;
constexpr int U = 16384;
constexpr int TB = 36864;
constexpr int OFF_RING = 8 * U, OFF_Z = 12 * U, OFF_XB = 12 * U, OFF_T = 13 * U, OFF_D = OFF_T;
constexpr int OFF_BAR = 14 * U, OFF_SP = OFF_BAR + 512, OFF_G = OFF_SP + 1024 + 128;
constexpr int SMEM_BYTES = OFF_G + 512;
constexpr int B_FX = 0, B_FA = 8, B_FT = 12, B_Z = 16, B_W = 24, B_HX = 25, B_TL = 26, B_HP = 27, B_WR = 31, B_E0 = 35;
constexpr int B_EA = 36, B_ET = 40, B_PZ = 44, B_RDY = 46, B_FE = 47;
constexpr int B_T = 51, B_XS = 52, B_G = 54, B_RD0 = 55, NBAR = 56;
__host__ __device__ constexpr int rslot(int n) { return n & 3; }
__host__ __device__ constexpr int rpar(int n) { return (n >> 2) & 1; }

__global__ void __cluster_dims__(2, 1, 1) __launch_bounds__(512, 1)
fused_kernel(Work* __restrict__ ws, const uint16_t* __restrict__ dtab, const __nv_bfloat16* __restrict__ w_r, const __nv_bfloat16* __restrict__ w_i,
             const __nv_bfloat16* __restrict__ gate_w, const __nv_bfloat16* __restrict__ x, __nv_bfloat16* __restrict__ out,
             const __grid_constant__ Maps maps) {
  extern __shared__ __align__(1024) uint8_t smem[];
  if (threadIdx.x < 32 && elect_one()) {
#pragma unroll
    for (int i = 0; i < PF0; i++) asm volatile("prefetch.tensormap [%0];" ::"l"((const char*)&maps + i * 128) : "memory");
  }
  const uint32_t sb = smem_u32(smem);
  const uint32_t bars = sb + OFF_BAR;
  const int tid = threadIdx.x, lane = tid & 31;
  const int warp = __shfl_sync(0xffffffffu, tid >> 5, 0);
  const bool helper = blockIdx.x >= 128;
  const int cl = (blockIdx.x >> 1) & 63, rank = blockIdx.x & 1;
  const int q4 = (cl & 1) | ((cl >> 2) & 2), rb = ((cl >> 1) & 3) | ((cl >> 4) << 2);
  const int j = 2 * q4 + rank;
  const int f_full = 448 * q4 + (rank ? 256 : 0);
  const int f_half = 448 * q4 + (rank ? 224 : 192);
  const int kg = 2 * j + (rb >> 3), tn = rb & 7;

  if (tid == 64) { PROF_EV(0); PROF_CK(40); }
  if (warp < 8) {
    if (!helper && tid < 32) {
      const int r = 16 * j + (tid & 15);
      asm volatile("prefetch.global.L2 [%0];" ::"l"(x + (size_t)(2 * rb + (r >> 6) + 32 * (r & 63)) * 512 + 64 * (tid >> 4)));
    }
    asm volatile("barrier.cluster.arrive.relaxed.aligned;" ::: "memory");
    asm volatile("setmaxnreg.inc.sync.aligned.u32 192;");
    if (!helper) {
      const int wg = warp >> 2, w = warp & 3, g = lane >> 2;
      const bool elect = (tid & 127) == 0;
      float cX[32], cA[64], cB[64], cC[64], ci[64], ct[64];
      const int zero = blockIdx.x >> 16;
      uint32_t h[56], yf[16];
      const uint32_t d0 = (sb & 0x3FFFF) >> 4;
      const uint32_t dK = d0 | (1u << 16), dN = d0 | (512u << 16);
      const uint32_t dX = dK + wg * 512;
      constexpr uint32_t RING = OFF_RING >> 4;
      auto waitA = [&](int n) { mbar_wait(bars + 8 * (B_FA + rslot(n)), rpar(n)); };
      auto freeA = [&](int n) { mbar_arrive_if(elect, bars + 8 * (B_EA + rslot(n))); };
      auto nop = [] {};

      asm volatile("bar.sync 0, 384;" ::: "memory");
#pragma unroll 1
      for (int i = 0; i < 4; i++) {
        const uint64_t dx = d128(dX + i * 2048), df = d128(dK + (OFF_XB >> 4) + (i & 1) * 1024);
        mbar_wait(bars + 8 * (B_FX + 2 * i), 0);
        wg_fence();
        mma_ss64<0, 0, 2>(cX, df, dx, i);
        mma_ss64<0, 0, 1>(cX, df + 2, dx + 2);
        wg_commit(); wg_wait<1>();
        mbar_arrive_if(elect && i, bars + 8 * (B_EA + rslot(i - 1)));
        mma_ss64<0, 0, 1>(cX, df + 4, dx + 4);
        mma_ss64<0, 0, 1>(cX, df + 6, dx + 6);
        if (i == 0 && tid == 0) PROF_EV(1);
        mbar_wait(bars + 8 * (B_FX + 2 * i + 1), 0);
        wg_fence();
#pragma unroll
        for (int k = 0; k < 4; k++) mma_ss64<0, 0, 1>(cX, df + (512 + k * 2), dx + (1024 + k * 2));
        wg_commit();
        waitA(i);
        wg_fence();
        const uint64_t da = d128(dX + i * 1024), db = d128(dN + RING + i * 1024);
        mma_ss128<0, 1, 2>(cA, da, db, i);
        wg_commit(); wg_wait<1>();
        mbar_arrive_if(elect, bars + 8 * (B_FE + i));
#pragma unroll
        for (int k = 1; k < 4; k++) mma_ss128<0, 1, 1>(cA, da + k * 2, db + k * 128);
        wg_commit();
      }
      fence_regs<0, 32>(cX);
#pragma unroll
      for (int e = 0; e < 16; e++) yf[e] = pack_pin(cX[2 * e], cX[2 * e + 1]);
      if (tid == 0) { PROF_EV(2); PROF_CK(42); }
      {
        waitA(4); mbar_wait(bars + 8 * B_E0, 0);
        const uint64_t de = d128(dN + (wg ? RING : OFF_XB >> 4));
        wg_fence();
        mma_rs128<0, 1, 0>(cB, yf[0], yf[1], yf[2], yf[3], de);
        wg_commit();
        wg_wait<1>();
        freeA(3);
#pragma unroll
        for (int k = 1; k < 4; k++) mma_rs128<0, 1, 1>(cB, yf[4 * k], yf[4 * k + 1], yf[4 * k + 2], yf[4 * k + 3], de + k * 128);
        wg_commit();
      }
      bool rel = false;
      auto acquire = [&](int n) {
        rel = elect;
        if (!mbar_try(bars + 8 * (B_FA + rslot(n)), rpar(n))) { wg_wait<0>(); freeA(n - 1); rel = false; waitA(n); }
      };
      auto freeP = [&](int n) { mbar_arrive_if(rel, bars + 8 * (B_EA + rslot(n - 1))); };
      auto ffn_step = [&](auto first, auto split, float (&acc)[64], int n, int kb, auto done, auto work) {
        constexpr int SPLIT = decltype(split)::value;
        acquire(n);
        wg_fence();
        const uint64_t dx = d128(dX + kb * 1024), db = d128(dN + RING + rslot(n) * 1024);
        mma_ss128<0, 1, decltype(first)::value>(acc, dx, db, kb);
#pragma unroll
        for (int k = 1; k < SPLIT; k++) mma_ss128<0, 1, 1>(acc, dx + k * 2, db + k * 128);
        wg_commit();
        work();
        wg_wait<1>();
        freeP(n);
        done();
        if (SPLIT < 4) {
          wg_fence();
#pragma unroll
          for (int k = SPLIT; k < 4; k++) mma_ss128<0, 1, 1>(acc, dx + k * 2, db + k * 128);
          wg_commit();
        }
      };
      {
        const int s0 = 2 * rb + wg, kr = 2 * ((s0 & 1) | ((s0 & 4) >> 1));
        const int m = lane >> 3, r = lane & 7;
        const uint32_t a0 = sb + OFF_XB + wg * 8192 + (((w >> 1) * 8 + (m >> 1)) * 2 + (w & 1)) * 256 + (m & 1) * 128 + ((r ^ (kr + (m & 1))) << 4);
        ffn_step(IC<1>(), IC<4>(), cA, 5, 4, [&] { fence_regs<0, 64>(cB); }, nop);
        asm volatile("bar.sync 5, 256;" ::: "memory");
        auto stage = [&](int i) {
          stsm4t(a0 + i * 1024, pack_bf16(cB[8 * i] - cB[34 + 8 * i], cB[8 * i + 1] - cB[35 + 8 * i]),
                 pack_bf16(cB[32 + 8 * i] + cB[8 * i + 2], cB[33 + 8 * i] + cB[8 * i + 3]),
                 pack_bf16(cB[8 * i + 4] - cB[38 + 8 * i], cB[8 * i + 5] - cB[39 + 8 * i]),
                 pack_bf16(cB[36 + 8 * i] + cB[8 * i + 6], cB[37 + 8 * i] + cB[8 * i + 7]));
          if (j == 0 && w == 0) {
            const uint32_t a1 = r ? sb + OFF_SP + 1024 : sb + OFF_SP + wg * 512 + (m & 1) * 256 + (m >> 1) * 128;
#pragma unroll
            for (int n = 2 * i; n < 2 * i + 2; n++)
              asm volatile("stmatrix.sync.aligned.m8n8.x4.shared.b16 [%0], {%1,%2,%3,%4};" ::"r"(a1 + ((n ^ (kr + (m >> 1)) ^ r) << 4)),
                           "r"(pack_bf16(cB[4 * n], cB[4 * n + 1])), "r"(pack_bf16(cB[4 * n + 2], cB[4 * n + 3])),
                           "r"(pack_bf16(cB[32 + 4 * n], cB[33 + 4 * n])), "r"(pack_bf16(cB[34 + 4 * n], cB[35 + 4 * n])) : "memory");
          }
        };
        auto publish = [&] {
          asm volatile("fence.proxy.async.shared::cta;" ::: "memory");
          __syncwarp();
          mbar_arrive_if(lane == 0, bars + 8 * (B_XS + wg));
          if (tid == 0) PROF_EV(3);
        };
        stage(0);
        ffn_step(IC<1>(), IC<FSPLIT>(), cA, 6, 5, nop, nop);
        stage(1);
        ffn_step(IC<1>(), IC<FSPLIT>(), cA, 7, 6, nop, nop);
        stage(2);
        ffn_step(IC<1>(), IC<2>(), cA, 8, 7, [&] { stage(3); }, nop);
        publish();
      }
      uint32_t gb0 = 0, gb1 = 0;
      uint32_t ob[2] = {0, 0};
      auto glu = [&](auto& acc, int half, int ho, int i0, int i1) {
#pragma unroll
        for (int i = i0; i < i1; i++)
          asm volatile("{\n.reg .b32 a, b;\ncvt.rn.relu.bf16x2.f32 a, %2, %1;\ncvt.rn.bf16x2.f32 b, %4, %3;\nmul.rn.bf16x2 a, a, b;\nmul.rn.bf16x2 %0, a, %5;\n}"
                       : "=r"(h[ho + i]) : "f"(acc[2 * i]), "f"(acc[2 * i + 1]), "f"(acc[half + 2 * i]), "f"(acc[half + 1 + 2 * i]), "r"(ob[i & 1]) : "memory");
      };
      ffn_step(IC<2>(), IC<1>(), cB, 9, zero, nop, nop);
#pragma unroll 1
      for (int kb = 1; kb < 8; kb++)
        ffn_step(IC<1>(), IC<FSPLIT>(), cB, 9 + kb, kb, nop, [&] {
          if (kb == GKB) {
            mbar_wait(bars + 8 * B_G, 0);
            asm volatile("ld.shared.u32 %0, [%2];\nld.shared.u32 %1, [%2+32];" : "=r"(gb0), "=r"(gb1) : "r"(sb + OFF_G + (wg * 64 + w * 16 + g) * 4) : "memory");
          } else if (kb == 5 + 2 * wg) {
            ob[0] = pack_bf16(1.0f - bf_hi(gb0), 1.0f - bf_hi(gb0)); ob[1] = pack_bf16(1.0f - bf_hi(gb1), 1.0f - bf_hi(gb1));
            glu(cA, 32, 0, 0, 16);
          }
        });
      const uint32_t tag = gb0 & 1;
      const float g0 = bf_hi(gb0), g1 = bf_hi(gb1);
      if (tid == 0) { PROF_EV(4); PROF_CK(43); }
      auto m_step = [&](auto first, int i) {
        acquire(17 + i);
        wg_fence();
        const uint64_t dx = d128(dX + i * 2048), dm = d64(dN + RING + rslot(17 + i) * 1024);
        mma_ss64<0, 1, decltype(first)::value>(ct, dx, dm);
#pragma unroll
        for (int k = 1; k < MSPLIT; k++) mma_ss64<0, 1, 1>(ct, dx + ((k >> 2) * 1024 + (k & 3) * 2), dm + k * 64);
        wg_commit();
        wg_wait<1>();
        freeP(17 + i);
        wg_fence();
#pragma unroll
        for (int k = MSPLIT; k < 8; k++) mma_ss64<0, 1, 1>(ct, dx + ((k >> 2) * 1024 + (k & 3) * 2), dm + k * 64);
        wg_commit();
      };
      m_step(IC<0>(), 0);
#pragma unroll 1
      for (int i = 1; i < 5; i++) {
        if (i == 1 + 2 * wg) glu(cB, 32, 16, 0, 16);
        if (i < 4) m_step(IC<1>(), i);
      }
      if (tid == 0) { PROF_EV(5); PROF_CK(44); }
      ffn_step(IC<0>(), IC<1>(), cC, 21, 0, nop, nop);
#pragma unroll 1
      for (int kb = 1; kb < 8; kb++)
        ffn_step(IC<1>(), IC<FSPLIT>(), cC, 21 + kb, kb, [&] { mbar_arrive_if(elect && !(kb & 1), bars + 8 * (B_ET + (kb >> 1) - 1)); }, [&] {
          if (kb == 1 + wg) glu(ct, 16, 48, 0, 8);
        });

      auto twait = [&](uint32_t bar, uint32_t par, int) { mbar_wait(bar, par); };
      const int fo = warp * 128 + lane;
      auto fetch = [&](uint4 (&pv)[4], int z) {
        twait(bars + 8 * (z < 4 ? B_Z + 2 * z + wg : z < 6 ? B_HP + z - 4 : B_HP + 2 + wg), 0, 8 + z);
        const uint8_t* src = smem + (z < 4 ? OFF_Z - z * U : z == 4 ? OFF_T : (z - 5) * U) + fo * 16;
#pragma unroll
        for (int i = 0; i < 4; i++) pv[i] = *(const uint4*)(src + i * 512);
      };
      const uint32_t peerZ = mapa(sb + OFF_Z + fo * 16, rank ^ 1), peerB = mapa(bars + 8 * (B_Z + wg), rank ^ 1);
      auto tile_mma = [&](auto off, int t, int k0, int k1, int init) {
        constexpr int O = decltype(off)::value;
        const uint64_t db = d128(dN + (t & 3) * (TB >> 4)), dw = db + rank * 256, dm = db + (rank ? 0 : 1536);
#pragma unroll
        for (int k = k0; k < k1; k++) {
          if (k == 0) mma_rs64<O, 1, 2>(ct, h[0], h[1], h[2], h[3], dw, init);
          else if (k < 14) mma_rs64<O, 1, 1>(ct, h[4 * k], h[4 * k + 1], h[4 * k + 2], h[4 * k + 3], k < 12 ? dw + k * 128 : dm + (k - 12) * 128);
          else mma_rs64<O, 1, 1>(ct, yf[4 * k - 56], yf[4 * k - 55], yf[4 * k - 54], yf[4 * k - 53], db + k * 128);
        }
      };
      uint4 pv[4] = {};
      auto tile = [&](auto off, int t) {
        constexpr int P = 32 - decltype(off)::value;
        const bool grid = t >= 4, pre = t >= 3 && t != 6;
        const int zo = grid ? t - 4 : t - 1, z = t - 3;
        const int owner = rb * 8 + 2 * ((q4 + zo + 1) & 3) + rank;
        uint4* dst = ws->part + (size_t)(owner * 3 + zo) * 1024 + fo;
        const uint32_t src = sb + OFF_Z - z * U + fo * 16;
        twait(bars + 8 * (B_FT + (t & 3)), t >> 2, t);
        wg_fence();
        tile_mma(off, t, 0, TH, zero);
        wg_commit();
        wg_wait<1>();
        mbar_arrive_if(elect && t < 6, bars + 8 * (B_ET + t - 1));
        if (t < 3) twait(bars + 8 * (t == 1 ? B_RD0 : B_RDY), 0, 14 + t);
        fence_regs<P, 32>(ct);
#pragma unroll
        for (int i = 0; i < 4; i++) {
          pv[i].x = (add_bf2(pv[i].x, pack_bf16(ct[P + 8 * i], ct[P + 8 * i + 1])) & ~(uint32_t)grid) | (tag & grid);
          pv[i].y = add_bf2(pv[i].y, pack_bf16(ct[P + 8 * i + 2], ct[P + 8 * i + 3]));
          pv[i].z = add_bf2(pv[i].z, pack_bf16(ct[P + 8 * i + 4], ct[P + 8 * i + 5]));
          pv[i].w = add_bf2(pv[i].w, pack_bf16(ct[P + 8 * i + 6], ct[P + 8 * i + 7]));
        }
        if (grid) {
#pragma unroll
          for (int i = 0; i < 4; i++)
            asm volatile("st.relaxed.gpu.global.v4.u32 [%0], {%1,%2,%3,%4};" ::"l"(dst + i * 32), "r"(pv[i].x), "r"(pv[i].y), "r"(pv[i].z), "r"(pv[i].w) : "memory");
          hint_add_if(lane == 0, &ws->cntP[32 * owner + 8 * (zo + (zo == 2 ? wg : 0))]);
        }
        auto share = [&](int i) {
          asm volatile("st.async.weak.shared::cluster.mbarrier::complete_tx::bytes.v4.b32 [%0], {%2,%3,%4,%5}, [%1];" ::"r"(peerZ - zo * U + i * 512),
                       "r"(peerB + 16 * zo), "r"(pv[i].x), "r"(pv[i].y), "r"(pv[i].z), "r"(pv[i].w) : "memory");
        };
#pragma unroll
        for (int i = 0; i < 4; i++) {
          if (!grid) share(i);
          wg_fence();
          tile_mma(off, t, TH + SPC * i, i < 3 ? TH + SPC * i + SPC : TL, 0);
        }
        wg_commit();
        if (pre) twait(bars + 8 * (B_Z + 2 * z + wg), 0, 8 + z);
        wg_fence();
#pragma unroll
        for (int i = 0; i < 4; i++) {
          asm volatile("{\n.reg .pred p;\nsetp.ne.b32 p, %5, 0;\nmov.b32 %0, 0;\nmov.b32 %1, 0;\nmov.b32 %2, 0;\nmov.b32 %3, 0;\n@p ld.shared.v4.u32 {%0,%1,%2,%3}, [%4];\n}"
                       : "=r"(pv[i].x), "=r"(pv[i].y), "=r"(pv[i].z), "=r"(pv[i].w) : "r"(src + i * 512), "r"((int)pre) : "memory");
          tile_mma(off, t, TL + i, i < 3 ? TL + 1 + i : 18, 0);
        }
        wg_commit();
      };
      asm volatile("barrier.cluster.wait.aligned;" ::: "memory");
      twait(bars + 8 * B_FT, 0, 0);
      wg_fence();
      tile_mma(IC<0>(), 0, 0, T0A, zero);
      wg_commit();
      waitA(29 + wg);
      wg_wait<1>();
      mbar_arrive_if(elect, bars + 8 * (B_ET + 3));
      glu(cC, 32, 32, 0, 16);
      if (tid == 0) PROF_EV(6);
      if (tid == 128) PROF_EV(27);
      mbar_wait(bars + 8 * (j == 0 ? B_T : B_TL), 0);
      if (tid == 0) { PROF_EV(7); PROF_CK(45); }
      wg_fence();
      {
        const uint64_t dt = d128(dN + (OFF_T >> 4) + wg * 512), de = d128(dK + RING + (1 + wg) * 1024);
        mma_ss64<0, 1, 0>(ci, de, dt);
        mma_ss64<32, 1, 0>(ci, de + 512, dt);
#pragma unroll
        for (int k = 1; k < 4; k++) {
          mma_ss64<0, 1, 1>(ci, de + k * 2, dt + k * 128);
          mma_ss64<32, 1, 1>(ci, de + (512 + k * 2), dt + k * 128);
        }
        wg_commit();
      }
      tile_mma(IC<0>(), 0, T0A, 14, 0);
      wg_commit();
      wg_wait<1>();
      if (elect) asm volatile("mbarrier.arrive.shared::cluster.b64 _, [%0];" ::"r"(mapa(bars + 8 * B_RDY, rank ^ 1)) : "memory");
      mbar_arrive_if(elect, bars + 8 * (B_PZ + 1));
      fence_regs<0, 64>(ci);
#pragma unroll
      for (int i = 0; i < 16; i++) {
        const float gg = ((i & 1) ? g1 : g0) * (2.0f / (2048.0f * 512.0f));
        if (i & 2) yf[i] = pack_pin((ci[2 * i] - ci[28 + 2 * i]) * gg, (ci[2 * i + 1] - ci[29 + 2 * i]) * gg);
        else yf[i] = pack_pin((ci[2 * i] + ci[36 + 2 * i]) * gg, (ci[2 * i + 1] + ci[37 + 2 * i]) * gg);
      }
      wg_fence();
      tile_mma(IC<0>(), 0, 14, 18, 0);
      wg_commit();
      if (tid == 0) PROF_EV(8);
      if (tid == 128) PROF_EV(28);
#pragma unroll 1
      for (int t = 1; t < 7; t += 2) {
        tile(IC<32>(), t);
        tile(IC<0>(), t + 1);
      }
      {
        uint4 p1[4], p2[4];
        auto acc4 = [&](uint4 (&d)[4], const uint4 (&a)[4]) {
#pragma unroll
          for (int i = 0; i < 4; i++) { d[i].x = add_bf2(d[i].x, a[i].x); d[i].y = add_bf2(d[i].y, a[i].y); d[i].z = add_bf2(d[i].z, a[i].z); d[i].w = add_bf2(d[i].w, a[i].w); }
        };
        auto add32 = [&](const uint4 (&a)[4]) {
#pragma unroll
          for (int i = 0; i < 4; i++) {
            const uint32_t u[4] = {a[i].x, a[i].y, a[i].z, a[i].w};
#pragma unroll
            for (int e = 0; e < 4; e++) { ct[32 + 8 * i + 2 * e] += bf_lo(u[e]); ct[33 + 8 * i + 2 * e] += bf_hi(u[e]); }
          }
        };
        twait(bars + 8 * (B_FT + 3), 1, 7);
        wg_fence();
        tile_mma(IC<32>(), 7, 0, TH, zero);
        wg_commit();
        wg_wait<1>();
        fence_regs<0, 32>(ct);
#pragma unroll
        for (int i = 0; i < 4; i++)
          asm volatile("st.async.weak.shared::cluster.mbarrier::complete_tx::bytes.v4.b32 [%0], {%2,%3,%4,%5}, [%1];" ::"r"(peerZ - 3 * U + i * 512), "r"(peerB + 48),
                       "r"(pack_bf16(ct[8 * i], ct[8 * i + 1])), "r"(pack_bf16(ct[8 * i + 2], ct[8 * i + 3])), "r"(pack_bf16(ct[8 * i + 4], ct[8 * i + 5])),
                       "r"(pack_bf16(ct[8 * i + 6], ct[8 * i + 7])) : "memory");
        wg_fence();
        tile_mma(IC<32>(), 7, TH, 9, 0);
        wg_commit();
        fetch(pv, 4);
        fetch(p1, 5);
        wg_fence();
        tile_mma(IC<32>(), 7, 9, 14, 0);
        wg_commit();
        uint32_t bad = 0;
#pragma unroll
        for (int i = 0; i < 4; i++) { bad |= (pv[i].x ^ tag) | (p1[i].x ^ tag); pv[i].x &= ~1u; p1[i].x &= ~1u; }
        acc4(pv, p1);
        fetch(p1, 3);
        wg_fence();
        tile_mma(IC<32>(), 7, 14, 18, 0);
        wg_commit();
        if (tid == 0) { PROF_EV(9); PROF_CK(46); }
        if (tid == 128) PROF_EV(29);
        fetch(p2, 6);
        if (tid == 0) PROF_EV(24);
        wg_wait<0>();
        fence_regs<32, 32>(ct);
#pragma unroll
        for (int i = 0; i < 4; i++) bad |= p2[i].x ^ tag;
        if (__any_sync(0xffffffffu, bad & 1)) {
          const uint4* src = ws->part + (size_t)(rb * 8 + j) * 3 * 1024 + fo;
          uint4 p0[4];
          int n = 0;
          do {
            bad = 0;
#pragma unroll
            for (int i = 0; i < 4; i++) {
              pv[i] = ld_x4(src + i * 32); p0[i] = ld_x4(src + 1024 + i * 32); p2[i] = ld_x4(src + 2048 + i * 32);
              bad |= (pv[i].x ^ tag) | (p0[i].x ^ tag) | (p2[i].x ^ tag);
            }
            if (++n > (1 << 21)) __trap();
          } while (__any_sync(0xffffffffu, bad & 1));
#pragma unroll
          for (int i = 0; i < 4; i++) { pv[i].x &= ~1u; p0[i].x &= ~1u; }
          acc4(pv, p0);
        }
#pragma unroll
        for (int i = 0; i < 4; i++) p2[i].x &= ~1u;
        acc4(p1, p2);
        add32(pv); add32(p1);
#pragma unroll
        for (int i = 0; i < 4; i++)
          pv[i] = make_uint4(pack_bf16(ct[32 + 8 * i], ct[33 + 8 * i]), pack_bf16(ct[34 + 8 * i], ct[35 + 8 * i]), pack_bf16(ct[36 + 8 * i], ct[37 + 8 * i]), pack_bf16(ct[38 + 8 * i], ct[39 + 8 * i]));
        if (tid == 0) PROF_EV(14);
        const uint32_t stg = sb + OFF_T + warp * 2048;
        const int mr = (lane & 7) + ((lane >> 3) & 1) * 8, mc = lane >> 4;
#pragma unroll
        for (int i = 0; i < 4; i++)
          asm volatile("stmatrix.sync.aligned.m8n8.x4.shared.b16 [%0], {%1,%2,%3,%4};" ::"r"(stg + mr * 128 + (((2 * i + mc) ^ (mr & 7)) << 4)), "r"(pv[i].x),
                       "r"(pv[i].y), "r"(pv[i].z), "r"(pv[i].w) : "memory");
        __syncwarp();
#pragma unroll
        for (int i = 0; i < 4; i++) {
          const int r = 4 * i + (lane >> 3), c = lane & 7;
          const uint4 v = *(const uint4*)(smem + OFF_T + warp * 2048 + r * 128 + ((c ^ (r & 7)) << 4));
          *(uint4*)(out + (size_t)(2 * rb + wg + 32 * (16 * w + r)) * 512 + 64 * j + 8 * c) = v;
        }
      }
      if (tid == 0) { PROF_EV(15); PROF_CK(41); }
      if (tid == 128) PROF_EV(30);
    }
  } else if (warp < 12) {
    asm volatile("setmaxnreg.dec.sync.aligned.u32 104;");
    asm volatile("barrier.cluster.arrive.relaxed.aligned;" ::: "memory");
    const int t = tid - 256, w = warp - 8;
    const uint32_t ep = ld_x1(&ws->epoch[blockIdx.x * 8]);
    const uint32_t tag = (ep + 1) & 1;
    auto w_issue = [&](const CUtensorMap* m) {

      if (elect_one()) { mbar_expect_tx(bars + 8 * (B_WR + w), 3072); tma4d(sb + OFF_T + w * 3072, m, bars + 8 * (B_WR + w), 16 * kg, 0, 2 * w, tn); }

          __syncwarp();
    };
    auto gate_rows = [&] {
      const int r = 16 * j + 4 * w + (lane >> 3);
      const uint4* pg = (const uint4*)gate_w + (lane & 7);
      {
        float a = 0.f;
        asm volatile("bar.sync 4, 256;" ::: "memory");
#pragma unroll 1
        for (int hf = 0; hf < 2; hf++) {
          uint4 v[4], u[4];
#pragma unroll
          for (int kb = 0; kb < 4; kb++) v[kb] = __ldg(pg + (4 * hf + kb) * 8);
          mbar_wait(bars + 8 * (B_FE + 1 + 2 * hf), 0);
          if (hf) w_issue(&maps.wr);
#pragma unroll
          for (int kb = 0; kb < 4; kb++) u[kb] = *(const uint4*)(smem + (4 * hf + kb) * U + r * 128 + (((lane ^ r) & 7) << 4));
#pragma unroll
          for (int kb = 0; kb < 4; kb++) {
            const uint32_t uu[4] = {u[kb].x, u[kb].y, u[kb].z, u[kb].w}, vv[4] = {v[kb].x, v[kb].y, v[kb].z, v[kb].w};
#pragma unroll
            for (int e = 0; e < 4; e++) {
              uint32_t pr;
              asm("mul.rn.bf16x2 %0, %1, %2;" : "=r"(pr) : "r"(uu[e]), "r"(vv[e]));
              a += bf_lo(pr) + bf_hi(pr);
            }
          }
        }
#pragma unroll
        for (int o = 4; o; o >>= 1) a += __shfl_xor_sync(0xffffffffu, a, o);
        if ((lane & 7) == 0)
          asm volatile("st.relaxed.gpu.global.u32 [%0], %1;" ::"l"(ws->gate + rb * 128 + r),
                       "r"(pack_bf16(0.f, __fdividef(1.0f, 1.0f + __expf(-bf_lo(pack_bf16(a, 0.f))))) | tag) : "memory");
        if (t == 0) PROF_EV(18);
      }
    };
    {
      const int g = lane >> 2, q = lane & 3;
      uint32_t wf[32];
      if (!helper) {
        gate_rows();
        const uint32_t wa = sb + OFF_T + w * (3072 + 4) + q * 48 + g * 2;
#pragma unroll 1
        for (int ri = 0; ri < 2; ri++) {
          mbar_wait(bars + 8 * (B_WR + w), ri);
#pragma unroll
          for (int n2 = 0; n2 < 32 / WB; n2++) {
            uint32_t v[WB];
#pragma unroll
            for (int i = 0; i < WB; i++) {
              const int e = n2 * WB + i;
              asm volatile("ld.shared.u16 %0, [%1];" : "=r"(v[i]) : "r"(wa + ((e >> 1) & 7) * 192 + (e & 1) * (1536 + 2) + (e >> 4) * 16) : "memory");
            }
#pragma unroll
            for (int i = 0; i < WB; i++) wf[n2 * WB + i] = __byte_perm(wf[n2 * WB + i], v[i], 0x5432);
            if (WSLEEP) { asm volatile("nanosleep.u32 %0;" ::"r"(WSLEEP + (v[WB - 1] >> 16)) : "memory"); }
          }
          __syncwarp();
          if (ri == 0) w_issue(&maps.wi);
        }
        asm volatile("bar.sync 1, 128;" ::: "memory");
        if (t == 0) PROF_EV(11);
      } else {
        asm volatile("bar.sync 4, 256;" ::: "memory");
        hint_wait(&ws->cntW[0], (ep + 1) * 128u);
        const uint32_t t0 = (uint32_t)clock();
#pragma unroll 1
        for (;;) {
          uint32_t bad = 0;
#pragma unroll
          for (int i = 0; i < 32; i++) {
            const float2 v = ld_x2((const float2*)ws->Wh + (i >> 4) * 2048 + 16 * w + g + 8 * (i & 1) + 64 * q + ((i >> 1) & 7) * 256);
            wf[i] = __float_as_uint(v.x); bad |= __float_as_uint(v.y) ^ tag;
          }
          if (!__any_sync(0xffffffffu, bad & 1)) break;
          spin_guard(t0);
        }
        if (t == 0) PROF_EV(11);
      }
      if (w == 0 && elect_one()) { mbar_expect_tx(bars + 8 * B_W, 8192); bulk_load(sb + OFF_D, dtab, 8192, bars + 8 * B_W); }
      asm volatile("barrier.cluster.wait.aligned;" ::: "memory");
      mbar_wait(bars + 8 * B_W, 0);
      mbar_wait(bars + 8 * B_HX, 0);
      if (t == 0) PROF_EV(12);
      const uint32_t dd = (sb & 0x3FFFF) >> 4;
      const uint64_t dF = d128((dd + (OFF_D >> 4)) | (512u << 16)), dI = d128((dd + (OFF_D >> 4)) | (1u << 16)), dA = d128((dd + (OFF_XB >> 4)) | (512u << 16));
      float az[32];
      const int zero = blockIdx.x >> 16;
      uint32_t pf[32];
#pragma unroll
      for (int mt = 0; mt < 2; mt++) {
        wg_fence();
        if (mt == 0) mma_ss64<0, 3, 0>(az, dA, dF);
        else mma_ss64<0, 3, 2>(az, dA + 512, dF, zero);
#pragma unroll
        for (int k = 1; k < 4; k++) mma_ss64<0, 3, 1>(az, dA + (mt * 512 + k * 128), dF + k * 128);
        wg_commit();
        wg_wait<0>();
        fence_regs<0, 32>(az);
#pragma unroll
        for (int i = 0; i < 16; i++) {
          const float wr = bf_lo(wf[16 * mt + i]), wi = bf_hi(wf[16 * mt + i]);
          pf[16 * mt + i] = pack_pin(fmaf(az[2 * i], wr, -az[2 * i + 1] * wi), fmaf(az[2 * i], wi, az[2 * i + 1] * wr));
        }
      }
      if (t == 0) PROF_EV(16);
      {
        const int m = lane >> 3, r = lane & 7;
        const int sl = 2 * (m >> 1) + ((r >> 1) & 1) + 4 * (r >> 2);
        const uint32_t a0 = sb + OFF_XB + (2 * w + (m & 1)) * 2048 + sl * 64;
        uint32_t pk[16];
#pragma unroll
        for (int mt = 0; mt < 3; mt++) {
          if (mt < 2) {
            wg_fence();
            mma_rs64<0, 0, 2>(az, pf[16 * mt], pf[16 * mt + 1], pf[16 * mt + 2], pf[16 * mt + 3], dI, mt ? (int)helper : zero);
#pragma unroll
            for (int k = 1; k < 4; k++) mma_rs64<0, 0, 1>(az, pf[16 * mt + 4 * k], pf[16 * mt + 4 * k + 1], pf[16 * mt + 4 * k + 2], pf[16 * mt + 4 * k + 3], dI + k * 2);
            wg_commit();
          }
          if (mt > 0 && !helper) {
#pragma unroll
            for (int i = 0; i < 4; i++) stsm4t(a0 + ((((mt - 1) * 2 + (r & 1)) ^ (sl >> 1)) << 4) + i * 512, pk[4 * i], pk[4 * i + 1], pk[4 * i + 2], pk[4 * i + 3]);
          }
          if (mt < 2) {
            wg_wait<0>();
            fence_regs<0, 32>(az);
#pragma unroll
            for (int i = 0; i < 16; i++) pk[i] = pack_pin(az[2 * i], az[2 * i + 1]);
          }
        }
      }
      if (helper) {
#pragma unroll
        for (int i = 0; i < 16; i++) {
          const int n = i >> 1, s0 = 8 * (n >> 1) + 2 * (n & 1) + (q & 1) + 4 * (q >> 1);
          if ((n & 1) == (int)(blockIdx.x & 1)) st_u2(ws->Ts + s0 * 64 + 16 * w + g + 8 * (i & 1), pack_bf16(az[2 * i], az[2 * i + 1]), tag);
        }
        __syncwarp();
        hint_add_if(lane == 0, &ws->cntH[0]);
        if (t == 0) { ws->epoch[blockIdx.x * 8] = ep + 1; PROF_EV(13); }
      } else {
        asm volatile("fence.proxy.async.shared::cta;" ::: "memory");
        __syncwarp();
        if (elect_one()) {
          if (t == 0) PROF_EV(17);
          if (SPACE) __nanosleep(SPACE * w);
          asm volatile("cp.async.bulk.tensor.3d.global.shared::cta.bulk_group [%0, {%2, %3, %4}], [%1];" ::"l"(&maps.ts), "r"(sb + OFF_XB + w * 4096),
                       "r"(32 * kg), "r"(0), "r"(8 * tn + 2 * w) : "memory");
          bulk_done_signal(&ws->cntT[32 * j]);
          asm volatile("mbarrier.arrive.shared::cluster.b64 _, [%0];" ::"r"(mapa(bars + 8 * B_RD0, rank ^ 1)) : "memory");
          if (t == 96) PROF_EV(13);
        }
        __syncwarp();
        if (j == 0) {
          hint_wait(&ws->cntH[0], (ep + 1) * 8u);
          const uint32_t t0 = (uint32_t)clock();
          float2 v;
          do { v = ld_x2((const float2*)ws->Ts + 2 * rb * 64 + t); spin_guard(t0); } while (__any_sync(0xffffffffu, (__float_as_uint(v.y) ^ tag) & 1));
          mbar_wait(bars + 8 * B_TL, 0);
          const uint32_t u = __float_as_uint(v.x);
          *(uint16_t*)(smem + OFF_T + t * 128 + ((t & 7) << 4)) = (uint16_t)u;
          *(uint16_t*)(smem + OFF_T + t * 128 + (((t & 7) ^ 1) << 4)) = (uint16_t)(u >> 16);
          asm volatile("fence.proxy.async.shared::cta;" ::: "memory");
          __syncwarp();
          mbar_arrive_if(lane == 0, bars + 8 * B_T);
        }
      }
    }
  } else {
    asm volatile("setmaxnreg.dec.sync.aligned.u32 24;");
    auto xf_load = [&](int q) {
      const uint32_t fb = bars + 8 * (B_FX + q);
      mbar_expect_tx(fb, U + 8192);
      tma3d(sb + q * U, &maps.x, fb, 64 * q, 0, 2 * rb);
      if (q >= 4) mbar_wait(bars + 8 * (B_FE + ((q - 4) >> 1)), 0);
      tma2d(sb + OFF_XB + (q & 3) * 8192, &maps.ft, fb, 64 * q, 64 * j);
    };
    if (elect_one()) {
      if (warp == 14) {
#pragma unroll
        for (int i = 0; i < B_FT; i++) mbar_init(bars + 8 * i, 1);
        asm volatile("fence.mbarrier_init.release.cluster;" ::: "memory");
        if (!helper) {
#pragma unroll 1
          for (int n = 0; n < 2; n++) {
            const uint32_t fb = bars + 8 * (B_FA + n);
            xf_load(2 * n); xf_load(2 * n + 1);
            mbar_expect_tx(fb, U);
            tma2d(sb + OFF_RING + n * U, &maps.g64, fb, f_full, 64 * n);
            tma2d(sb + OFF_RING + n * U + 8192, &maps.u64, fb, f_full, 64 * n);
          }
        }
      } else if (warp == 15) {
#pragma unroll
        for (int i = B_FT; i < NBAR; i++) mbar_init(bars + 8 * i, i < B_EA ? 1 : i < B_T ? 2 : 4);
#pragma unroll
        for (int i = 0; i < 8; i++) mbar_expect_tx(bars + 8 * (B_Z + i), U / 2);
        asm volatile("fence.mbarrier_init.release.cluster;" ::: "memory");
        asm volatile("fence.proxy.async.shared::cta;" ::: "memory");
      }
    }
    __syncwarp();
    asm volatile("bar.arrive 0, 384;" ::: "memory");
    asm volatile("bar.arrive 4, 256;" ::: "memory");
    __syncwarp();
    asm volatile("barrier.cluster.arrive.relaxed.aligned;" ::: "memory");
    asm volatile("bar.sync 3, 128;" ::: "memory");
    if (warp == 15 && !helper) {
        mbar_wait(bars + 8 * B_FE, 0);
        const uint32_t tag = (ld_x1(&ws->epoch[blockIdx.x * 8]) + 1) & 1;
        const int c = lane >> 4, jj = 16 * blockIdx.x + (lane & 15), jm = (2048 - jj) & 2047;
        const unsigned short* pr = (const unsigned short*)w_r + 256 * c;
        const unsigned short* pi = (const unsigned short*)w_i + 256 * c;
        const float wr = 0.25f * (bf_lo(__ldg(pr + jj * 257)) + bf_lo(__ldg(pr + jm * 257)));
        const float wi = 0.25f * (bf_lo(__ldg(pi + jj * 257)) - bf_lo(__ldg(pi + jm * 257)));
        st_u2(ws->Wh + c * 2048 + jj, c ? pack_bf16(-wi, wr) : pack_bf16(wr, wi), tag);
        __syncwarp();
        hint_add_if(lane == 0, &ws->cntW[0]);
        mbar_wait(bars + 8 * B_XS, 0);
        const uint32_t t0 = (uint32_t)clock();
        uint4 v;
        do { v = ld_x4(ws->gate + rb * 128 + 4 * lane); spin_guard(t0); } while (__any_sync(0xffffffffu, ((v.x ^ tag) | (v.y ^ tag) | (v.z ^ tag) | (v.w ^ tag)) & 1));
        *(uint4*)(smem + OFF_G + lane * 16) = v;
        __syncwarp();
        mbar_arrive_if(lane < 4, bars + 8 * B_G);
      }
    auto part_load = [&](int i, unsigned ep1) {
      const uint32_t bytes = i < 2 ? U : U / 2;
      mbar_wait(bars + 8 * (B_PZ + (i == 0)), 0);
      mbar_expect_tx(bars + 8 * (B_HP + i), bytes);
      flag_wait(&ws->cntP[32 * (rb * 8 + j) + 8 * i], ep1 * (i < 2 ? 8u : 4u));
      bulk_load(sb + (i == 0 ? OFF_T : i == 1 ? 0 : i * (U / 2)), ws->part + (size_t)(rb * 8 + j) * 3072 + (i < 2 ? i * 1024 : 1024 + i * 512), bytes, bars + 8 * (B_HP + i));
      if (i == 2) PROF_EV(26);
    };
    if ((!helper || warp == 15) && elect_one()) {
      if (warp < 14) {
        const int p = warp - 12;
#pragma unroll 1
        for (int i = 4 + p; i < 13; i += 2) asm volatile("prefetch.tensormap [%0];" ::"l"((const char*)&maps + i * 128) : "memory");
#pragma unroll 1
        for (int n = 2; n < 31; n++) {
          const bool table = n == 4 || n >= 29;
          const bool half = n >= 17 && n < 21;
          const int q = n < 4 ? n : n < 17 ? n - 1 : n - 5;
          const CUtensorMap* m = table ? &maps.e : half ? &maps.g32 + p : &maps.g64 + p;
          const int c0 = table ? 0 : half ? f_half : f_full + 64 * (q >> 3);
          const int c1 = table ? (2 * rb + ((n & 1) ^ 1)) * 128 + 64 * p : half ? 128 * (n - 17) : 64 * (q & 7);
          const uint32_t fb = bars + 8 * (B_FA + (n & 3)), dst = sb + OFF_RING + (n & 3) * U + p * 8192;
          if (n < 4) mbar_wait(bars + 8 * (B_FE + n - 2), 0);
          else mbar_wait(bars + 8 * (B_EA + (n & 3)), ((n >> 2) & 1) ^ 1);
          tma2d(dst, m, fb, c0, c1);
          if (p == 0) mbar_expect_tx(fb, U);
        }
        part_load(2 + p, ld_x1(&ws->epoch[blockIdx.x * 8]) + 1);
      } else if (warp == 15) {
        const unsigned ep1 = ld_x1(&ws->epoch[blockIdx.x * 8]) + 1;
        flag_wait(&ws->cntX[helper ? 0 : 32 * j], ep1 * 16u);
        PROF_EV(22);
        mbar_expect_tx(bars + 8 * B_HX, U);
        bulk_load(sb + OFF_XB, ws->X + (size_t)(helper ? 128 : kg * 8 + tn) * 8192, U, bars + 8 * B_HX);
        if (!helper) {
          flag_wait(&ws->cntT[32 * j], ep1 * 64u);
          PROF_EV(23);
          mbar_expect_tx(bars + 8 * B_TL, U);
          tma3d(sb + OFF_T, &maps.t, bars + 8 * B_TL, 64 * j, 0, 2 * rb);
          part_load(0, ep1); part_load(1, ep1);
          mbar_wait(bars + 8 * (B_HP + 2), 0); mbar_wait(bars + 8 * (B_HP + 3), 0);
          ws->epoch[blockIdx.x * 8] = ep1;
        }
      } else {
#pragma unroll 1
        for (int q = 4; q < 8; q++) xf_load(q);
        mbar_wait(bars + 8 * (B_FE + 2), 0);
        mbar_expect_tx(bars + 8 * B_E0, U);
        tma2d(sb + OFF_XB, &maps.e, bars + 8 * B_E0, 0, 2 * rb * 128);
        tma2d(sb + OFF_XB + 8192, &maps.e, bars + 8 * B_E0, 0, 2 * rb * 128 + 64);
#pragma unroll 1
        for (int h2 = 0; h2 < 2; h2++) {
          const int s0 = 2 * rb + h2, sg = (s0 & ~6) | ((s0 & 2) << 1) | ((s0 & 4) >> 1);
          mbar_wait(bars + 8 * (B_XS + h2), 0);
#pragma unroll 1
          for (int c = 0; c < 2; c++) {
            asm volatile("cp.async.bulk.tensor.4d.global.shared::cta.bulk_group [%0, {%2, %3, %4, %5}], [%1];" ::"l"(&maps.xs),
                         "r"(sb + OFF_XB + h2 * 8192 + c * 4096), "r"(0), "r"(sg), "r"(0), "r"(16 * j + 8 * c) : "memory");
            if (j == 0)
              asm volatile("cp.async.bulk.global.shared::cta.bulk_group [%0], [%1], 256;" ::"l"(ws->X + 128 * 8192 + c * 4096 + sg * 128),
                           "r"(sb + OFF_SP + h2 * 512 + c * 256) : "memory");
            if (SPACE && h2 + c < 2) __nanosleep(SPACE);
          }
        }
        bulk_done_signal(&ws->cntX[32 * j]);
        PROF_EV(20);
#pragma unroll 1
        for (int t = 0; t < 8; t++) {
          const int i = t < 3 ? t + 1 : t < 6 ? t - 2 : 0;
          const int col = 64 * (2 * ((q4 + i) & 3) + ((t < 3 || t == 6) ? 1 - rank : rank));
          const uint32_t fb = bars + 8 * (B_FT + (t & 3)), dst = sb + (t & 3) * TB;
          mbar_wait(bars + 8 * (B_ET + (t < 3 ? t + 1 : t & 3)), t >> 2);
          mbar_expect_tx(fb, TB);
          tma2d(dst, &maps.d224, fb, col, 224 * j);
          if (t < 2) mbar_wait(bars + 8 * (B_ET + t + 1), 0);
          tma2d(dst + 28672, &maps.ft, fb, col, 64 * j);
        }
      }
    }
  }
}

typedef CUresult (*EncodeFn)(CUtensorMap*, CUtensorMapDataType, cuuint32_t, void*, const cuuint64_t*, const cuuint64_t*, const cuuint32_t*,
                             const cuuint32_t*, CUtensorMapInterleave, CUtensorMapSwizzle, CUtensorMapL2promotion, CUtensorMapFloatOOBfill);

static void encode(EncodeFn f, CUtensorMap* m, const void* base, int rank, const cuuint64_t* dims, const cuuint64_t* strides, const cuuint32_t* box,
                   CUtensorMapSwizzle sw) {
  cuuint32_t es[5] = {1, 1, 1, 1, 1};
  f(m, CU_TENSOR_MAP_DATA_TYPE_BFLOAT16, rank, (void*)base, dims, strides, box, es, CU_TENSOR_MAP_INTERLEAVE_NONE, sw,
    CU_TENSOR_MAP_L2_PROMOTION_L2_128B, CU_TENSOR_MAP_FLOAT_OOB_FILL_NONE);
}

extern "C" void kernel_launch(void* const* d_in, const int* in_sizes, int n_in, void* d_out, int out_size) {
  (void)in_sizes; (void)n_in; (void)out_size;
  const __nv_bfloat16* x = (const __nv_bfloat16*)d_in[0];
  const __nv_bfloat16* w_r = (const __nv_bfloat16*)d_in[1];
  const __nv_bfloat16* w_i = (const __nv_bfloat16*)d_in[2];
  const __nv_bfloat16* Wg = (const __nv_bfloat16*)d_in[4];
  const __nv_bfloat16* Wu = (const __nv_bfloat16*)d_in[5];
  const __nv_bfloat16* Wd = (const __nv_bfloat16*)d_in[6];
  const __nv_bfloat16* gw = (const __nv_bfloat16*)d_in[7];

  void* fp = nullptr; cudaDriverEntryPointQueryResult qr;
  cudaGetDriverEntryPoint("cuTensorMapEncodeTiled", &fp, cudaEnableDefault, &qr);
  EncodeFn enc = (EncodeFn)fp;
  void *pFT, *pET, *pDT, *pW;
  cudaGetSymbolAddress(&pDT, g_DT); cudaGetSymbolAddress(&pW, g_work);
  void *pX = ((Work*)pW)->X, *pT = ((Work*)pW)->T;
  cudaGetSymbolAddress(&pFT, g_FT); cudaGetSymbolAddress(&pET, g_ET);

  Maps mp;
  const CUtensorMapSwizzle S128 = CU_TENSOR_MAP_SWIZZLE_128B, S64 = CU_TENSOR_MAP_SWIZZLE_64B;
  { cuuint64_t d[3] = {512, 64, 32}, s[2] = {32768, 1024}; cuuint32_t b[3] = {64, 64, 2}; encode(enc, &mp.x, x, 3, d, s, b, S128); }
  { cuuint64_t d[2] = {512, 512}, s[1] = {1024}; cuuint32_t b[2] = {64, 64}; encode(enc, &mp.ft, pFT, 2, d, s, b, S128); }
  { cuuint64_t d[4] = {128, 32, 2, 129}, s[3] = {256, 8192, 16384}; cuuint32_t b[4] = {128, 1, 2, 8}; encode(enc, &mp.xs, pX, 4, d, s, b, CU_TENSOR_MAP_SWIZZLE_NONE); }
  { cuuint64_t d[3] = {512, 32, 64}, s[2] = {65536, 1024}; cuuint32_t b[3] = {32, 32, 2}; encode(enc, &mp.ts, pT, 3, d, s, b, S64); }
  { cuuint64_t d[3] = {512, 64, 32}, s[2] = {1024, 65536}; cuuint32_t b[3] = {64, 64, 2}; encode(enc, &mp.t, pT, 3, d, s, b, S128); }
  { cuuint64_t d[2] = {64, 4096}, s[1] = {128}; cuuint32_t b[2] = {64, 64}; encode(enc, &mp.e, pET, 2, d, s, b, S128); }
  { cuuint64_t d[2] = {1792, 512}, s[1] = {3584}; cuuint32_t b[2] = {64, 64}, b2[2] = {32, 128};
    encode(enc, &mp.g64, Wg, 2, d, s, b, S128); encode(enc, &mp.u64, Wu, 2, d, s, b, S128);
    encode(enc, &mp.g32, Wg, 2, d, s, b2, S64); encode(enc, &mp.u32, Wu, 2, d, s, b2, S64); }
  { cuuint64_t d[2] = {512, 1792}, s[1] = {1024}; cuuint32_t b[2] = {64, 224}; encode(enc, &mp.d224, Wd, 2, d, s, b, S128); }
  { cuuint64_t d[4] = {264, 32, 8, 8}, s[3] = {32896, 512, 4112}; cuuint32_t b[4] = {24, 32, 2, 1};
    encode(enc, &mp.wr, w_r, 4, d, s, b, CU_TENSOR_MAP_SWIZZLE_NONE); encode(enc, &mp.wi, w_i, 4, d, s, b, CU_TENSOR_MAP_SWIZZLE_NONE); }

  cudaFuncSetAttribute(fused_kernel, cudaFuncAttributeMaxDynamicSharedMemorySize, SMEM_BYTES);
  fused_kernel<<<NCTA, 512, SMEM_BYTES>>>((Work*)pW, (const uint16_t*)pDT, w_r, w_i, gw, x, (__nv_bfloat16*)d_out, mp);
}
```

```cpp
#include <cuda_runtime.h>
#include <cuda_bf16.h>
#include <cuda.h>
#include <stdint.h>

namespace tbl {
constexpr double PI = 3.14159265358979323846264338327950288;
constexpr double sin_s(double x) { double t = x, s = x; for (int n = 1; n < 12; n++) { t *= -x * x / ((2 * n) * (2 * n + 1)); s += t; } return s; }
constexpr double cos_s(double x) { double t = 1, s = 1; for (int n = 1; n < 12; n++) { t *= -x * x / ((2 * n - 1) * (2 * n)); s += t; } return s; }
constexpr double cos2048(int m) {
  m &= 2047; if (m > 1024) m = 2048 - m;
  bool neg = false; if (m > 512) { m = 1024 - m; neg = true; }
  double v = (m <= 256) ? cos_s(2 * PI * m / 2048) : sin_s(2 * PI * (512 - m) / 2048);
  return neg ? -v : v;
}
constexpr uint16_t to_bf16(double v) {
  if (v == 0) return 0;
  uint16_t s = 0; if (v < 0) { s = 0x8000; v = -v; }
  int e = 0; while (v >= 2) { v /= 2; e++; } while (v < 1) { v *= 2; e--; }
  double m = (v - 1) * 128; int mi = (int)m; double fr = m - mi;
  if (fr > 0.5 || (fr == 0.5 && (mi & 1))) mi++;
  if (mi == 128) { mi = 0; e++; }
  return (uint16_t)(s | ((e + 127) << 7) | mi);
}
struct CosT { uint16_t v[2048]; constexpr CosT() : v() { for (int i = 0; i < 2048; i++) v[i] = to_bf16(cos2048(i)); } };
struct alignas(1024) FT {
  uint16_t v[512 * 512];
  constexpr FT() : v() {
    CosT c;
    for (int r = 0; r < 512; r++) {
      int k = (r >> 4) * 8 + (r & 7), e = (r >> 3) & 1;
      int mul = 4 * k, add = e ? 512 : 0;
      if (k == 0 && e == 1) { mul = 1024; add = 0; }
      for (int d = 0; d < 512; d++) v[r * 512 + d] = c.v[(d * mul + add) & 2047];
    }
  }
};
struct alignas(1024) ET {
  uint16_t v[2048 * 128];
  constexpr ET() : v() {
    CosT c;
    for (int s = 0; s < 2048; s++)
      for (int j = 0; j < 64; j++) {
        const int o = (s & 31) * 8192 + (s >> 5) * 64 + j;
        v[o] = c.v[(s * j) & 2047]; v[o + 4096] = c.v[(s * j + 512) & 2047];
      }
  }
};
struct alignas(1024) DT {
  uint16_t v[64 * 64];
  constexpr DT() : v() {
    CosT c;
    for (int r = 0; r < 64; r++)
      for (int n = 0; n < 64; n++) {
        const int sg = r >> 1, s0 = (sg & ~6) | ((sg & 2) << 1) | ((sg & 4) >> 1), e = r & 1, f = n & 1;
        const int m = 64 * s0 * (n >> 1) + (e == f ? 0 : e ? -512 : 512);
        v[r * 64 + (((n >> 3) ^ (r & 7)) << 3) + (n & 7)] = c.v[m & 2047];
      }
  }
};
}

__device__ constexpr tbl::FT g_FT = tbl::FT();
__device__ constexpr tbl::ET g_ET = tbl::ET();
__device__ constexpr tbl::DT g_DT = tbl::DT();

struct alignas(1024) Work {
  unsigned epoch[132 * 8];
  unsigned cntX[8 * 32], cntT[8 * 32], cntP[128 * 32], cntW[32], cntH[32];
  alignas(16) float gate[16 * 128];
  alignas(16) uint2 Wh[2 * 2048];
  alignas(16) uint2 Ts[32 * 64];
  alignas(1024) uint16_t X[129 * 8192];
  alignas(1024) uint16_t T[32 * 64 * 512];
  alignas(1024) uint4 part[128 * 3 * 1024];
};
__device__ Work g_work;
#define PROF_EV(i) do {} while (0)
#define PROF_CK(i) do {} while (0)

__device__ __forceinline__ uint32_t smem_u32(const void* p) { return (uint32_t)__cvta_generic_to_shared(p); }
__device__ __forceinline__ void mbar_init(uint32_t bar, uint32_t cnt) { asm volatile("mbarrier.init.shared::cta.b64 [%0], %1;" ::"r"(bar), "r"(cnt)); }
__device__ __forceinline__ void mbar_expect_tx(uint32_t bar, uint32_t bytes) { asm volatile("mbarrier.arrive.expect_tx.shared::cta.b64 _, [%0], %1;" ::"r"(bar), "r"(bytes) : "memory"); }
__device__ __forceinline__ void mbar_arrive(uint32_t bar) { asm volatile("mbarrier.arrive.shared::cta.b64 _, [%0];" ::"r"(bar) : "memory"); }
__device__ __forceinline__ bool elect_one() {
  uint32_t p;
  asm volatile("{\n.reg .pred p;\nelect.sync _|p, 0xffffffff;\nselp.u32 %0, 1, 0, p;\n}" : "=r"(p));
  return p;
}
__device__ __forceinline__ void mbar_arrive_if(bool p, uint32_t bar) {
  asm volatile("{\n.reg .pred p;\nsetp.ne.b32 p, %1, 0;\n@p mbarrier.arrive.shared::cta.b64 _, [%0];\n}" ::"r"(bar), "r"((int)p) : "memory");
}
__device__ __forceinline__ void hint_add_if(bool p, unsigned* a) {
  asm volatile("{\n.reg .pred p;\nsetp.ne.b32 p, %1, 0;\n@p red.relaxed.gpu.global.add.u32 [%0], 1;\n}" ::"l"(a), "r"((int)p) : "memory");
}
__device__ __forceinline__ bool mbar_try(uint32_t bar, uint32_t parity) {
  uint32_t ok;
  asm volatile("{\n.reg .pred p;\nmbarrier.test_wait.parity.shared::cta.b64 p, [%1], %2;\nselp.u32 %0, 1, 0, p;\n}" : "=r"(ok) : "r"(bar), "r"(parity) : "memory");
  return ok;
}
__device__ __forceinline__ void mbar_wait(uint32_t bar, uint32_t parity) {
  asm volatile(
      "{\n.reg .pred p;\n.reg .u32 n;\nmov.u32 n, 0;\n"
      "W_LOOP:\nmbarrier.try_wait.parity.shared::cta.b64 p, [%0], %1;\n@p bra W_DONE;\n"
      "add.u32 n, n, 1;\nsetp.lt.u32 p, n, 0x40000;\n@p bra W_LOOP;\ntrap;\nW_DONE:\n}" ::"r"(bar), "r"(parity) : "memory");
}
__device__ __forceinline__ void bulk_load(uint32_t dst, const void* src, uint32_t bytes, uint32_t bar) {
  asm volatile("cp.async.bulk.shared::cluster.global.mbarrier::complete_tx::bytes [%0], [%1], %2, [%3];" ::"r"(dst), "l"(src), "r"(bytes), "r"(bar) : "memory");
}
__device__ __forceinline__ void spin_guard(uint32_t t0) { if ((uint32_t)clock() - t0 > (1u << 30)) __trap(); }
__device__ __forceinline__ float2 ld_x2(const float2* p) { float2 v; asm volatile("ld.relaxed.gpu.global.v2.f32 {%0,%1}, [%2];" : "=f"(v.x), "=f"(v.y) : "l"(p) : "memory"); return v; }
__device__ __forceinline__ void st_u2(uint2* p, uint32_t a, uint32_t b) { asm volatile("st.relaxed.gpu.global.v2.u32 [%0], {%1,%2};" ::"l"(p), "r"(a), "r"(b) : "memory"); }
__device__ __forceinline__ uint32_t ld_x1(const void* p) { uint32_t v; asm volatile("ld.relaxed.gpu.global.u32 %0, [%1];" : "=r"(v) : "l"(p) : "memory"); return v; }
__device__ __forceinline__ uint4 ld_x4(const void* p) { uint4 v; asm volatile("ld.relaxed.gpu.global.v4.u32 {%0,%1,%2,%3}, [%4];" : "=r"(v.x), "=r"(v.y), "=r"(v.z), "=r"(v.w) : "l"(p) : "memory"); return v; }
__device__ __forceinline__ uint32_t mapa(uint32_t a, uint32_t cta) { uint32_t r; asm volatile("mapa.shared::cluster.u32 %0, %1, %2;" : "=r"(r) : "r"(a), "r"(cta)); return r; }
__device__ __forceinline__ void stsm4t(uint32_t a, uint32_t r0, uint32_t r1, uint32_t r2, uint32_t r3) {
  asm volatile("stmatrix.sync.aligned.m8n8.x4.trans.shared.b16 [%0], {%1,%2,%3,%4};" ::"r"(a), "r"(r0), "r"(r1), "r"(r2), "r"(r3) : "memory");
}
__device__ __forceinline__ void hint_add(unsigned* p) { asm volatile("red.relaxed.gpu.global.add.u32 [%0], 1;" ::"l"(p) : "memory"); }
__device__ __forceinline__ void hint_wait(const unsigned* p, unsigned target) {
  const uint32_t t0 = (uint32_t)clock();
  while ((int)(ld_x1(p) - target) < 0) spin_guard(t0);
}
__device__ __forceinline__ void bulk_done_signal(unsigned* p) {
  asm volatile("cp.async.bulk.commit_group;\ncp.async.bulk.wait_group 0;\nfence.proxy.async.global;" ::: "memory");
  hint_add(p);
}
__device__ __forceinline__ void flag_wait(const unsigned* p, unsigned target) {
  hint_wait(p, target);
  asm volatile("fence.proxy.async.global;" ::: "memory");
}
__device__ __forceinline__ void tma2d(uint32_t dst, const CUtensorMap* m, uint32_t bar, int c0, int c1) {
  asm volatile("cp.async.bulk.tensor.2d.shared::cluster.global.mbarrier::complete_tx::bytes [%0], [%1, {%3, %4}], [%2];" ::"r"(dst), "l"(m), "r"(bar), "r"(c0), "r"(c1) : "memory");
}
__device__ __forceinline__ void tma3d(uint32_t dst, const CUtensorMap* m, uint32_t bar, int c0, int c1, int c2) {
  asm volatile("cp.async.bulk.tensor.3d.shared::cluster.global.mbarrier::complete_tx::bytes [%0], [%1, {%3, %4, %5}], [%2];" ::"r"(dst), "l"(m), "r"(bar), "r"(c0), "r"(c1), "r"(c2) : "memory");
}
__device__ __forceinline__ void tma4d(uint32_t dst, const CUtensorMap* m, uint32_t bar, int c0, int c1, int c2, int c3) {
  asm volatile("cp.async.bulk.tensor.4d.shared::cluster.global.mbarrier::complete_tx::bytes [%0], [%1, {%3, %4, %5, %6}], [%2];" ::"r"(dst), "l"(m), "r"(bar), "r"(c0), "r"(c1), "r"(c2), "r"(c3) : "memory");
}
__device__ __forceinline__ void wg_fence() { asm volatile("wgmma.fence.sync.aligned;" ::: "memory"); }
__device__ __forceinline__ void wg_commit() { asm volatile("wgmma.commit_group.sync.aligned;" ::: "memory"); }
template <int N> __device__ __forceinline__ void wg_wait() { asm volatile("wgmma.wait_group.sync.aligned %0;" ::"n"(N) : "memory"); }
template <int O, int N, int NN> __device__ __forceinline__ void fence_regs(float (&d)[NN]) {
#pragma unroll
  for (int i = 0; i < N; i++) asm volatile("" : "+f"(d[O + i])::"memory");
}
__device__ __forceinline__ uint32_t pack_bf16(float lo, float hi) {
  uint32_t r; asm("cvt.rn.bf16x2.f32 %0, %1, %2;" : "=r"(r) : "f"(hi), "f"(lo)); return r;
}
__device__ __forceinline__ uint32_t pack_pin(float lo, float hi) {
  uint32_t r; asm volatile("cvt.rn.bf16x2.f32 %0, %1, %2;" : "=r"(r) : "f"(hi), "f"(lo) : "memory"); return r;
}
__device__ __forceinline__ uint32_t add_bf2(uint32_t a, uint32_t b) { uint32_t r; asm("add.rn.bf16x2 %0, %1, %2;" : "=r"(r) : "r"(a), "r"(b)); return r; }
__device__ __forceinline__ float bf_lo(uint32_t u) { return __uint_as_float(u << 16); }
__device__ __forceinline__ float bf_hi(uint32_t u) { return __uint_as_float(u & 0xffff0000u); }

__device__ __forceinline__ uint64_t d128(uint32_t lo) { uint64_t d; asm("mov.b64 %0, {%1, 0x40000040};" : "=l"(d) : "r"(lo)); return d; }
__device__ __forceinline__ uint64_t d64(uint32_t lo) { uint64_t d; asm("mov.b64 %0, {%1, 0x80000020};" : "=l"(d) : "r"(lo)); return d; }
template<int O,int TB,int ACC,int NN> __device__ __forceinline__ void mma_ss64(float (&d)[NN], uint64_t da, uint64_t db, int sd = 0){
  if constexpr (ACC == 1) asm volatile("wgmma.mma_async.sync.aligned.m64n64k16.f32.bf16.bf16 {%0,%1,%2,%3,%4,%5,%6,%7,%8,%9,%10,%11,%12,%13,%14,%15,%16,%17,%18,%19,%20,%21,%22,%23,%24,%25,%26,%27,%28,%29,%30,%31}, %32, %33, 1, 1, 1, %35, %34;"
   : "+f"(d[O+0]), "+f"(d[O+1]), "+f"(d[O+2]), "+f"(d[O+3]), "+f"(d[O+4]), "+f"(d[O+5]), "+f"(d[O+6]), "+f"(d[O+7]), "+f"(d[O+8]), "+f"(d[O+9]), "+f"(d[O+10]), "+f"(d[O+11]), "+f"(d[O+12]), "+f"(d[O+13]), "+f"(d[O+14]), "+f"(d[O+15]), "+f"(d[O+16]), "+f"(d[O+17]), "+f"(d[O+18]), "+f"(d[O+19]), "+f"(d[O+20]), "+f"(d[O+21]), "+f"(d[O+22]), "+f"(d[O+23]), "+f"(d[O+24]), "+f"(d[O+25]), "+f"(d[O+26]), "+f"(d[O+27]), "+f"(d[O+28]), "+f"(d[O+29]), "+f"(d[O+30]), "+f"(d[O+31])
   : "l"(da), "l"(db), "n"(TB & 1), "n"(TB >> 1));
  else if constexpr (ACC == 0) asm volatile("wgmma.mma_async.sync.aligned.m64n64k16.f32.bf16.bf16 {%0,%1,%2,%3,%4,%5,%6,%7,%8,%9,%10,%11,%12,%13,%14,%15,%16,%17,%18,%19,%20,%21,%22,%23,%24,%25,%26,%27,%28,%29,%30,%31}, %32, %33, 0, 1, 1, %35, %34;"
   : "=f"(d[O+0]), "=f"(d[O+1]), "=f"(d[O+2]), "=f"(d[O+3]), "=f"(d[O+4]), "=f"(d[O+5]), "=f"(d[O+6]), "=f"(d[O+7]), "=f"(d[O+8]), "=f"(d[O+9]), "=f"(d[O+10]), "=f"(d[O+11]), "=f"(d[O+12]), "=f"(d[O+13]), "=f"(d[O+14]), "=f"(d[O+15]), "=f"(d[O+16]), "=f"(d[O+17]), "=f"(d[O+18]), "=f"(d[O+19]), "=f"(d[O+20]), "=f"(d[O+21]), "=f"(d[O+22]), "=f"(d[O+23]), "=f"(d[O+24]), "=f"(d[O+25]), "=f"(d[O+26]), "=f"(d[O+27]), "=f"(d[O+28]), "=f"(d[O+29]), "=f"(d[O+30]), "=f"(d[O+31])
   : "l"(da), "l"(db), "n"(TB & 1), "n"(TB >> 1));
  else asm volatile("{\n.reg .pred p;\nsetp.ne.b32 p, %36, 0;\nwgmma.mma_async.sync.aligned.m64n64k16.f32.bf16.bf16 {%0,%1,%2,%3,%4,%5,%6,%7,%8,%9,%10,%11,%12,%13,%14,%15,%16,%17,%18,%19,%20,%21,%22,%23,%24,%25,%26,%27,%28,%29,%30,%31}, %32, %33, p, 1, 1, %35, %34;\n}"
   : "+f"(d[O+0]), "+f"(d[O+1]), "+f"(d[O+2]), "+f"(d[O+3]), "+f"(d[O+4]), "+f"(d[O+5]), "+f"(d[O+6]), "+f"(d[O+7]), "+f"(d[O+8]), "+f"(d[O+9]), "+f"(d[O+10]), "+f"(d[O+11]), "+f"(d[O+12]), "+f"(d[O+13]), "+f"(d[O+14]), "+f"(d[O+15]), "+f"(d[O+16]), "+f"(d[O+17]), "+f"(d[O+18]), "+f"(d[O+19]), "+f"(d[O+20]), "+f"(d[O+21]), "+f"(d[O+22]), "+f"(d[O+23]), "+f"(d[O+24]), "+f"(d[O+25]), "+f"(d[O+26]), "+f"(d[O+27]), "+f"(d[O+28]), "+f"(d[O+29]), "+f"(d[O+30]), "+f"(d[O+31])
   : "l"(da), "l"(db), "n"(TB & 1), "n"(TB >> 1), "r"(sd));
}
template<int O,int TB,int ACC,int NN> __device__ __forceinline__ void mma_rs64(float (&d)[NN], uint32_t a0, uint32_t a1, uint32_t a2, uint32_t a3, uint64_t db, int sd = 0){
  if constexpr (ACC == 1) asm volatile("wgmma.mma_async.sync.aligned.m64n64k16.f32.bf16.bf16 {%0,%1,%2,%3,%4,%5,%6,%7,%8,%9,%10,%11,%12,%13,%14,%15,%16,%17,%18,%19,%20,%21,%22,%23,%24,%25,%26,%27,%28,%29,%30,%31}, {%32,%33,%34,%35}, %36, 1, 1, 1, %37;"
   : "+f"(d[O+0]), "+f"(d[O+1]), "+f"(d[O+2]), "+f"(d[O+3]), "+f"(d[O+4]), "+f"(d[O+5]), "+f"(d[O+6]), "+f"(d[O+7]), "+f"(d[O+8]), "+f"(d[O+9]), "+f"(d[O+10]), "+f"(d[O+11]), "+f"(d[O+12]), "+f"(d[O+13]), "+f"(d[O+14]), "+f"(d[O+15]), "+f"(d[O+16]), "+f"(d[O+17]), "+f"(d[O+18]), "+f"(d[O+19]), "+f"(d[O+20]), "+f"(d[O+21]), "+f"(d[O+22]), "+f"(d[O+23]), "+f"(d[O+24]), "+f"(d[O+25]), "+f"(d[O+26]), "+f"(d[O+27]), "+f"(d[O+28]), "+f"(d[O+29]), "+f"(d[O+30]), "+f"(d[O+31])
   : "r"(a0), "r"(a1), "r"(a2), "r"(a3), "l"(db), "n"(TB));
  else if constexpr (ACC == 0) asm volatile("wgmma.mma_async.sync.aligned.m64n64k16.f32.bf16.bf16 {%0,%1,%2,%3,%4,%5,%6,%7,%8,%9,%10,%11,%12,%13,%14,%15,%16,%17,%18,%19,%20,%21,%22,%23,%24,%25,%26,%27,%28,%29,%30,%31}, {%32,%33,%34,%35}, %36, 0, 1, 1, %37;"
   : "=f"(d[O+0]), "=f"(d[O+1]), "=f"(d[O+2]), "=f"(d[O+3]), "=f"(d[O+4]), "=f"(d[O+5]), "=f"(d[O+6]), "=f"(d[O+7]), "=f"(d[O+8]), "=f"(d[O+9]), "=f"(d[O+10]), "=f"(d[O+11]), "=f"(d[O+12]), "=f"(d[O+13]), "=f"(d[O+14]), "=f"(d[O+15]), "=f"(d[O+16]), "=f"(d[O+17]), "=f"(d[O+18]), "=f"(d[O+19]), "=f"(d[O+20]), "=f"(d[O+21]), "=f"(d[O+22]), "=f"(d[O+23]), "=f"(d[O+24]), "=f"(d[O+25]), "=f"(d[O+26]), "=f"(d[O+27]), "=f"(d[O+28]), "=f"(d[O+29]), "=f"(d[O+30]), "=f"(d[O+31])
   : "r"(a0), "r"(a1), "r"(a2), "r"(a3), "l"(db), "n"(TB));
  else asm volatile("{\n.reg .pred p;\nsetp.ne.b32 p, %38, 0;\nwgmma.mma_async.sync.aligned.m64n64k16.f32.bf16.bf16 {%0,%1,%2,%3,%4,%5,%6,%7,%8,%9,%10,%11,%12,%13,%14,%15,%16,%17,%18,%19,%20,%21,%22,%23,%24,%25,%26,%27,%28,%29,%30,%31}, {%32,%33,%34,%35}, %36, p, 1, 1, %37;\n}"
   : "+f"(d[O+0]), "+f"(d[O+1]), "+f"(d[O+2]), "+f"(d[O+3]), "+f"(d[O+4]), "+f"(d[O+5]), "+f"(d[O+6]), "+f"(d[O+7]), "+f"(d[O+8]), "+f"(d[O+9]), "+f"(d[O+10]), "+f"(d[O+11]), "+f"(d[O+12]), "+f"(d[O+13]), "+f"(d[O+14]), "+f"(d[O+15]), "+f"(d[O+16]), "+f"(d[O+17]), "+f"(d[O+18]), "+f"(d[O+19]), "+f"(d[O+20]), "+f"(d[O+21]), "+f"(d[O+22]), "+f"(d[O+23]), "+f"(d[O+24]), "+f"(d[O+25]), "+f"(d[O+26]), "+f"(d[O+27]), "+f"(d[O+28]), "+f"(d[O+29]), "+f"(d[O+30]), "+f"(d[O+31])
   : "r"(a0), "r"(a1), "r"(a2), "r"(a3), "l"(db), "n"(TB), "r"(sd));
}
template<int O,int TB,int ACC,int NN> __device__ __forceinline__ void mma_ss128(float (&d)[NN], uint64_t da, uint64_t db, int sd = 0){
  if constexpr (ACC == 1) asm volatile("wgmma.mma_async.sync.aligned.m64n128k16.f32.bf16.bf16 {%0,%1,%2,%3,%4,%5,%6,%7,%8,%9,%10,%11,%12,%13,%14,%15,%16,%17,%18,%19,%20,%21,%22,%23,%24,%25,%26,%27,%28,%29,%30,%31,%32,%33,%34,%35,%36,%37,%38,%39,%40,%41,%42,%43,%44,%45,%46,%47,%48,%49,%50,%51,%52,%53,%54,%55,%56,%57,%58,%59,%60,%61,%62,%63}, %64, %65, 1, 1, 1, %67, %66;"
   : "+f"(d[O+0]), "+f"(d[O+1]), "+f"(d[O+2]), "+f"(d[O+3]), "+f"(d[O+4]), "+f"(d[O+5]), "+f"(d[O+6]), "+f"(d[O+7]), "+f"(d[O+8]), "+f"(d[O+9]), "+f"(d[O+10]), "+f"(d[O+11]), "+f"(d[O+12]), "+f"(d[O+13]), "+f"(d[O+14]), "+f"(d[O+15]), "+f"(d[O+16]), "+f"(d[O+17]), "+f"(d[O+18]), "+f"(d[O+19]), "+f"(d[O+20]), "+f"(d[O+21]), "+f"(d[O+22]), "+f"(d[O+23]), "+f"(d[O+24]), "+f"(d[O+25]), "+f"(d[O+26]), "+f"(d[O+27]), "+f"(d[O+28]), "+f"(d[O+29]), "+f"(d[O+30]), "+f"(d[O+31]), "+f"(d[O+32]), "+f"(d[O+33]), "+f"(d[O+34]), "+f"(d[O+35]), "+f"(d[O+36]), "+f"(d[O+37]), "+f"(d[O+38]), "+f"(d[O+39]), "+f"(d[O+40]), "+f"(d[O+41]), "+f"(d[O+42]), "+f"(d[O+43]), "+f"(d[O+44]), "+f"(d[O+45]), "+f"(d[O+46]), "+f"(d[O+47]), "+f"(d[O+48]), "+f"(d[O+49]), "+f"(d[O+50]), "+f"(d[O+51]), "+f"(d[O+52]), "+f"(d[O+53]), "+f"(d[O+54]), "+f"(d[O+55]), "+f"(d[O+56]), "+f"(d[O+57]), "+f"(d[O+58]), "+f"(d[O+59]), "+f"(d[O+60]), "+f"(d[O+61]), "+f"(d[O+62]), "+f"(d[O+63])
   : "l"(da), "l"(db), "n"(TB & 1), "n"(TB >> 1));
  else if constexpr (ACC == 0) asm volatile("wgmma.mma_async.sync.aligned.m64n128k16.f32.bf16.bf16 {%0,%1,%2,%3,%4,%5,%6,%7,%8,%9,%10,%11,%12,%13,%14,%15,%16,%17,%18,%19,%20,%21,%22,%23,%24,%25,%26,%27,%28,%29,%30,%31,%32,%33,%34,%35,%36,%37,%38,%39,%40,%41,%42,%43,%44,%45,%46,%47,%48,%49,%50,%51,%52,%53,%54,%55,%56,%57,%58,%59,%60,%61,%62,%63}, %64, %65, 0, 1, 1, %67, %66;"
   : "=f"(d[O+0]), "=f"(d[O+1]), "=f"(d[O+2]), "=f"(d[O+3]), "=f"(d[O+4]), "=f"(d[O+5]), "=f"(d[O+6]), "=f"(d[O+7]), "=f"(d[O+8]), "=f"(d[O+9]), "=f"(d[O+10]), "=f"(d[O+11]), "=f"(d[O+12]), "=f"(d[O+13]), "=f"(d[O+14]), "=f"(d[O+15]), "=f"(d[O+16]), "=f"(d[O+17]), "=f"(d[O+18]), "=f"(d[O+19]), "=f"(d[O+20]), "=f"(d[O+21]), "=f"(d[O+22]), "=f"(d[O+23]), "=f"(d[O+24]), "=f"(d[O+25]), "=f"(d[O+26]), "=f"(d[O+27]), "=f"(d[O+28]), "=f"(d[O+29]), "=f"(d[O+30]), "=f"(d[O+31]), "=f"(d[O+32]), "=f"(d[O+33]), "=f"(d[O+34]), "=f"(d[O+35]), "=f"(d[O+36]), "=f"(d[O+37]), "=f"(d[O+38]), "=f"(d[O+39]), "=f"(d[O+40]), "=f"(d[O+41]), "=f"(d[O+42]), "=f"(d[O+43]), "=f"(d[O+44]), "=f"(d[O+45]), "=f"(d[O+46]), "=f"(d[O+47]), "=f"(d[O+48]), "=f"(d[O+49]), "=f"(d[O+50]), "=f"(d[O+51]), "=f"(d[O+52]), "=f"(d[O+53]), "=f"(d[O+54]), "=f"(d[O+55]), "=f"(d[O+56]), "=f"(d[O+57]), "=f"(d[O+58]), "=f"(d[O+59]), "=f"(d[O+60]), "=f"(d[O+61]), "=f"(d[O+62]), "=f"(d[O+63])
   : "l"(da), "l"(db), "n"(TB & 1), "n"(TB >> 1));
  else asm volatile("{\n.reg .pred p;\nsetp.ne.b32 p, %68, 0;\nwgmma.mma_async.sync.aligned.m64n128k16.f32.bf16.bf16 {%0,%1,%2,%3,%4,%5,%6,%7,%8,%9,%10,%11,%12,%13,%14,%15,%16,%17,%18,%19,%20,%21,%22,%23,%24,%25,%26,%27,%28,%29,%30,%31,%32,%33,%34,%35,%36,%37,%38,%39,%40,%41,%42,%43,%44,%45,%46,%47,%48,%49,%50,%51,%52,%53,%54,%55,%56,%57,%58,%59,%60,%61,%62,%63}, %64, %65, p, 1, 1, %67, %66;\n}"
   : "+f"(d[O+0]), "+f"(d[O+1]), "+f"(d[O+2]), "+f"(d[O+3]), "+f"(d[O+4]), "+f"(d[O+5]), "+f"(d[O+6]), "+f"(d[O+7]), "+f"(d[O+8]), "+f"(d[O+9]), "+f"(d[O+10]), "+f"(d[O+11]), "+f"(d[O+12]), "+f"(d[O+13]), "+f"(d[O+14]), "+f"(d[O+15]), "+f"(d[O+16]), "+f"(d[O+17]), "+f"(d[O+18]), "+f"(d[O+19]), "+f"(d[O+20]), "+f"(d[O+21]), "+f"(d[O+22]), "+f"(d[O+23]), "+f"(d[O+24]), "+f"(d[O+25]), "+f"(d[O+26]), "+f"(d[O+27]), "+f"(d[O+28]), "+f"(d[O+29]), "+f"(d[O+30]), "+f"(d[O+31]), "+f"(d[O+32]), "+f"(d[O+33]), "+f"(d[O+34]), "+f"(d[O+35]), "+f"(d[O+36]), "+f"(d[O+37]), "+f"(d[O+38]), "+f"(d[O+39]), "+f"(d[O+40]), "+f"(d[O+41]), "+f"(d[O+42]), "+f"(d[O+43]), "+f"(d[O+44]), "+f"(d[O+45]), "+f"(d[O+46]), "+f"(d[O+47]), "+f"(d[O+48]), "+f"(d[O+49]), "+f"(d[O+50]), "+f"(d[O+51]), "+f"(d[O+52]), "+f"(d[O+53]), "+f"(d[O+54]), "+f"(d[O+55]), "+f"(d[O+56]), "+f"(d[O+57]), "+f"(d[O+58]), "+f"(d[O+59]), "+f"(d[O+60]), "+f"(d[O+61]), "+f"(d[O+62]), "+f"(d[O+63])
   : "l"(da), "l"(db), "n"(TB & 1), "n"(TB >> 1), "r"(sd));
}
template<int O,int TB,int ACC,int NN> __device__ __forceinline__ void mma_rs128(float (&d)[NN], uint32_t a0, uint32_t a1, uint32_t a2, uint32_t a3, uint64_t db, int sd = 0){
  if constexpr (ACC == 1) asm volatile("wgmma.mma_async.sync.aligned.m64n128k16.f32.bf16.bf16 {%0,%1,%2,%3,%4,%5,%6,%7,%8,%9,%10,%11,%12,%13,%14,%15,%16,%17,%18,%19,%20,%21,%22,%23,%24,%25,%26,%27,%28,%29,%30,%31,%32,%33,%34,%35,%36,%37,%38,%39,%40,%41,%42,%43,%44,%45,%46,%47,%48,%49,%50,%51,%52,%53,%54,%55,%56,%57,%58,%59,%60,%61,%62,%63}, {%64,%65,%66,%67}, %68, 1, 1, 1, %69;"
   : "+f"(d[O+0]), "+f"(d[O+1]), "+f"(d[O+2]), "+f"(d[O+3]), "+f"(d[O+4]), "+f"(d[O+5]), "+f"(d[O+6]), "+f"(d[O+7]), "+f"(d[O+8]), "+f"(d[O+9]), "+f"(d[O+10]), "+f"(d[O+11]), "+f"(d[O+12]), "+f"(d[O+13]), "+f"(d[O+14]), "+f"(d[O+15]), "+f"(d[O+16]), "+f"(d[O+17]), "+f"(d[O+18]), "+f"(d[O+19]), "+f"(d[O+20]), "+f"(d[O+21]), "+f"(d[O+22]), "+f"(d[O+23]), "+f"(d[O+24]), "+f"(d[O+25]), "+f"(d[O+26]), "+f"(d[O+27]), "+f"(d[O+28]), "+f"(d[O+29]), "+f"(d[O+30]), "+f"(d[O+31]), "+f"(d[O+32]), "+f"(d[O+33]), "+f"(d[O+34]), "+f"(d[O+35]), "+f"(d[O+36]), "+f"(d[O+37]), "+f"(d[O+38]), "+f"(d[O+39]), "+f"(d[O+40]), "+f"(d[O+41]), "+f"(d[O+42]), "+f"(d[O+43]), "+f"(d[O+44]), "+f"(d[O+45]), "+f"(d[O+46]), "+f"(d[O+47]), "+f"(d[O+48]), "+f"(d[O+49]), "+f"(d[O+50]), "+f"(d[O+51]), "+f"(d[O+52]), "+f"(d[O+53]), "+f"(d[O+54]), "+f"(d[O+55]), "+f"(d[O+56]), "+f"(d[O+57]), "+f"(d[O+58]), "+f"(d[O+59]), "+f"(d[O+60]), "+f"(d[O+61]), "+f"(d[O+62]), "+f"(d[O+63])
   : "r"(a0), "r"(a1), "r"(a2), "r"(a3), "l"(db), "n"(TB));
  else if constexpr (ACC == 0) asm volatile("wgmma.mma_async.sync.aligned.m64n128k16.f32.bf16.bf16 {%0,%1,%2,%3,%4,%5,%6,%7,%8,%9,%10,%11,%12,%13,%14,%15,%16,%17,%18,%19,%20,%21,%22,%23,%24,%25,%26,%27,%28,%29,%30,%31,%32,%33,%34,%35,%36,%37,%38,%39,%40,%41,%42,%43,%44,%45,%46,%47,%48,%49,%50,%51,%52,%53,%54,%55,%56,%57,%58,%59,%60,%61,%62,%63}, {%64,%65,%66,%67}, %68, 0, 1, 1, %69;"
   : "=f"(d[O+0]), "=f"(d[O+1]), "=f"(d[O+2]), "=f"(d[O+3]), "=f"(d[O+4]), "=f"(d[O+5]), "=f"(d[O+6]), "=f"(d[O+7]), "=f"(d[O+8]), "=f"(d[O+9]), "=f"(d[O+10]), "=f"(d[O+11]), "=f"(d[O+12]), "=f"(d[O+13]), "=f"(d[O+14]), "=f"(d[O+15]), "=f"(d[O+16]), "=f"(d[O+17]), "=f"(d[O+18]), "=f"(d[O+19]), "=f"(d[O+20]), "=f"(d[O+21]), "=f"(d[O+22]), "=f"(d[O+23]), "=f"(d[O+24]), "=f"(d[O+25]), "=f"(d[O+26]), "=f"(d[O+27]), "=f"(d[O+28]), "=f"(d[O+29]), "=f"(d[O+30]), "=f"(d[O+31]), "=f"(d[O+32]), "=f"(d[O+33]), "=f"(d[O+34]), "=f"(d[O+35]), "=f"(d[O+36]), "=f"(d[O+37]), "=f"(d[O+38]), "=f"(d[O+39]), "=f"(d[O+40]), "=f"(d[O+41]), "=f"(d[O+42]), "=f"(d[O+43]), "=f"(d[O+44]), "=f"(d[O+45]), "=f"(d[O+46]), "=f"(d[O+47]), "=f"(d[O+48]), "=f"(d[O+49]), "=f"(d[O+50]), "=f"(d[O+51]), "=f"(d[O+52]), "=f"(d[O+53]), "=f"(d[O+54]), "=f"(d[O+55]), "=f"(d[O+56]), "=f"(d[O+57]), "=f"(d[O+58]), "=f"(d[O+59]), "=f"(d[O+60]), "=f"(d[O+61]), "=f"(d[O+62]), "=f"(d[O+63])
   : "r"(a0), "r"(a1), "r"(a2), "r"(a3), "l"(db), "n"(TB));
  else asm volatile("{\n.reg .pred p;\nsetp.ne.b32 p, %70, 0;\nwgmma.mma_async.sync.aligned.m64n128k16.f32.bf16.bf16 {%0,%1,%2,%3,%4,%5,%6,%7,%8,%9,%10,%11,%12,%13,%14,%15,%16,%17,%18,%19,%20,%21,%22,%23,%24,%25,%26,%27,%28,%29,%30,%31,%32,%33,%34,%35,%36,%37,%38,%39,%40,%41,%42,%43,%44,%45,%46,%47,%48,%49,%50,%51,%52,%53,%54,%55,%56,%57,%58,%59,%60,%61,%62,%63}, {%64,%65,%66,%67}, %68, p, 1, 1, %69;\n}"
   : "+f"(d[O+0]), "+f"(d[O+1]), "+f"(d[O+2]), "+f"(d[O+3]), "+f"(d[O+4]), "+f"(d[O+5]), "+f"(d[O+6]), "+f"(d[O+7]), "+f"(d[O+8]), "+f"(d[O+9]), "+f"(d[O+10]), "+f"(d[O+11]), "+f"(d[O+12]), "+f"(d[O+13]), "+f"(d[O+14]), "+f"(d[O+15]), "+f"(d[O+16]), "+f"(d[O+17]), "+f"(d[O+18]), "+f"(d[O+19]), "+f"(d[O+20]), "+f"(d[O+21]), "+f"(d[O+22]), "+f"(d[O+23]), "+f"(d[O+24]), "+f"(d[O+25]), "+f"(d[O+26]), "+f"(d[O+27]), "+f"(d[O+28]), "+f"(d[O+29]), "+f"(d[O+30]), "+f"(d[O+31]), "+f"(d[O+32]), "+f"(d[O+33]), "+f"(d[O+34]), "+f"(d[O+35]), "+f"(d[O+36]), "+f"(d[O+37]), "+f"(d[O+38]), "+f"(d[O+39]), "+f"(d[O+40]), "+f"(d[O+41]), "+f"(d[O+42]), "+f"(d[O+43]), "+f"(d[O+44]), "+f"(d[O+45]), "+f"(d[O+46]), "+f"(d[O+47]), "+f"(d[O+48]), "+f"(d[O+49]), "+f"(d[O+50]), "+f"(d[O+51]), "+f"(d[O+52]), "+f"(d[O+53]), "+f"(d[O+54]), "+f"(d[O+55]), "+f"(d[O+56]), "+f"(d[O+57]), "+f"(d[O+58]), "+f"(d[O+59]), "+f"(d[O+60]), "+f"(d[O+61]), "+f"(d[O+62]), "+f"(d[O+63])
   : "r"(a0), "r"(a1), "r"(a2), "r"(a3), "l"(db), "n"(TB), "r"(sd));
}

#define NEARLY 0
#define XAHEAD 3
#define HEADN 6
#define WBATCH 1
#define WB 8
#define WSLEEP 20
#define XSPREAD 4
#define NOSEND 0
#define MSPLIT 2
#define PFALL 1
#define L2PF 0
#define STAG 0
#define EPF 2
#define XNB 2
#define FNB 0
#define GNB 0
#define TH 4
#define PF0 4
#define FSPLIT 1
#define MGLU 1
#define SPC 2
#define TL 14
#define GKB 4
#define T0A 8
#define TGATE 1
#define ZLATE 0
#define EARLYADD 1
#define SPACE 100
#define WPF 1
#define WAFTER 7
#define WPACE 0
#define GATE_AT 4
#define TPACE 40
#define PFMODE 0
#define MAPMODE 1
template <int V> struct IC { static constexpr int value = V; };
struct Maps { CUtensorMap x, ft, g64, u64, e, wr, wi, xs, ts, t, g32, u32, d224; };

constexpr int NCTA = 130;
constexpr int U = 16384;
constexpr int TB = 36864;
constexpr int OFF_RING = 8 * U, OFF_Z = 12 * U, OFF_XB = 12 * U, OFF_T = 13 * U, OFF_D = OFF_T;
constexpr int OFF_BAR = 14 * U, OFF_SP = OFF_BAR + 512, OFF_G = OFF_SP + 1024 + 128;
constexpr int SMEM_BYTES = OFF_G + 512;
constexpr int B_FX = 0, B_FA = 8, B_FT = 12, B_Z = 16, B_W = 24, B_HX = 25, B_TL = 26, B_HP = 27, B_WR = 31, B_E0 = 35;
constexpr int B_EA = 36, B_ET = 40, B_PZ = 44, B_RDY = 46, B_FE = 47;
constexpr int B_T = 51, B_XS = 52, B_G = 54, B_RD0 = 55, NBAR = 56;
__host__ __device__ constexpr int rslot(int n) { return n & 3; }
__host__ __device__ constexpr int rpar(int n) { return (n >> 2) & 1; }

__global__ void __cluster_dims__(2, 1, 1) __launch_bounds__(512, 1)
fused_kernel(Work* __restrict__ ws, const uint16_t* __restrict__ dtab, const __nv_bfloat16* __restrict__ w_r, const __nv_bfloat16* __restrict__ w_i,
             const __nv_bfloat16* __restrict__ gate_w, const __nv_bfloat16* __restrict__ x, __nv_bfloat16* __restrict__ out,
             const __grid_constant__ Maps maps) {
  extern __shared__ __align__(1024) uint8_t smem[];
  if (threadIdx.x < 32 && elect_one()) {
#pragma unroll
    for (int i = 0; i < PF0; i++) asm volatile("prefetch.tensormap [%0];" ::"l"((const char*)&maps + i * 128) : "memory");
  }
  const uint32_t sb = smem_u32(smem);
  const uint32_t bars = sb + OFF_BAR;
  const int tid = threadIdx.x, lane = tid & 31;
  const int warp = __shfl_sync(0xffffffffu, tid >> 5, 0);
  const bool helper = blockIdx.x >= 128;
  const int cl = (blockIdx.x >> 1) & 63, rank = blockIdx.x & 1;
  const int q4 = (cl & 1) | ((cl >> 2) & 2), rb = ((cl >> 1) & 3) | ((cl >> 4) << 2);
  const int j = 2 * q4 + rank;
  const int f_full = 448 * q4 + (rank ? 256 : 0);
  const int f_half = 448 * q4 + (rank ? 224 : 192);
  const int kg = 2 * j + (rb >> 3), tn = rb & 7;

  if (tid == 64) { PROF_EV(0); PROF_CK(40); }
  if (warp < 8) {
    if (!helper && tid < 32) {
      const int r = 16 * j + (tid & 15);
      asm volatile("prefetch.global.L2 [%0];" ::"l"(x + (size_t)(2 * rb + (r >> 6) + 32 * (r & 63)) * 512 + 64 * (tid >> 4)));
    }
    asm volatile("barrier.cluster.arrive.relaxed.aligned;" ::: "memory");
    asm volatile("setmaxnreg.inc.sync.aligned.u32 192;");
    if (!helper) {
      const int wg = warp >> 2, w = warp & 3, g = lane >> 2;
      const bool elect = (tid & 127) == 0;
      float cX[32], cA[64], cB[64], cC[64], ci[64], ct[64];
      const int zero = blockIdx.x >> 16;
      uint32_t h[56], yf[16];
      const uint32_t d0 = (sb & 0x3FFFF) >> 4;
      const uint32_t dK = d0 | (1u << 16), dN = d0 | (512u << 16);
      const uint32_t dX = dK + wg * 512;
      constexpr uint32_t RING = OFF_RING >> 4;
      auto waitA = [&](int n) { mbar_wait(bars + 8 * (B_FA + rslot(n)), rpar(n)); };
      auto freeA = [&](int n) { mbar_arrive_if(elect, bars + 8 * (B_EA + rslot(n))); };
      auto nop = [] {};

      asm volatile("bar.sync 0, 384;" ::: "memory");
#pragma unroll 1
      for (int i = 0; i < 4; i++) {
        const uint64_t dx = d128(dX + i * 2048), df = d128(dK + (OFF_XB >> 4) + (i & 1) * 1024);
        mbar_wait(bars + 8 * (B_FX + 2 * i), 0);
        wg_fence();
        mma_ss64<0, 0, 2>(cX, df, dx, i);
        mma_ss64<0, 0, 1>(cX, df + 2, dx + 2);
        wg_commit(); wg_wait<1>();
        mbar_arrive_if(elect && i, bars + 8 * (B_EA + rslot(i - 1)));
        mma_ss64<0, 0, 1>(cX, df + 4, dx + 4);
        mma_ss64<0, 0, 1>(cX, df + 6, dx + 6);
        if (i == 0 && tid == 0) PROF_EV(1);
        mbar_wait(bars + 8 * (B_FX + 2 * i + 1), 0);
        wg_fence();
#pragma unroll
        for (int k = 0; k < 4; k++) mma_ss64<0, 0, 1>(cX, df + (512 + k * 2), dx + (1024 + k * 2));
        wg_commit();
        waitA(i);
        wg_fence();
        const uint64_t da = d128(dX + i * 1024), db = d128(dN + RING + i * 1024);
        mma_ss128<0, 1, 2>(cA, da, db, i);
        wg_commit(); wg_wait<1>();
        mbar_arrive_if(elect, bars + 8 * (B_FE + i));
#pragma unroll
        for (int k = 1; k < 4; k++) mma_ss128<0, 1, 1>(cA, da + k * 2, db + k * 128);
        wg_commit();
      }
      fence_regs<0, 32>(cX);
#pragma unroll
      for (int e = 0; e < 16; e++) yf[e] = pack_pin(cX[2 * e], cX[2 * e + 1]);
      if (tid == 0) { PROF_EV(2); PROF_CK(42); }
      {
        waitA(4); mbar_wait(bars + 8 * B_E0, 0);
        const uint64_t de = d128(dN + (wg ? RING : OFF_XB >> 4));
        wg_fence();
        mma_rs128<0, 1, 0>(cB, yf[0], yf[1], yf[2], yf[3], de);
        wg_commit();
        wg_wait<1>();
        freeA(3);
#pragma unroll
        for (int k = 1; k < 4; k++) mma_rs128<0, 1, 1>(cB, yf[4 * k], yf[4 * k + 1], yf[4 * k + 2], yf[4 * k + 3], de + k * 128);
        wg_commit();
      }
      bool rel = false;
      auto acquire = [&](int n) {
        rel = elect;
        if (!mbar_try(bars + 8 * (B_FA + rslot(n)), rpar(n))) { wg_wait<0>(); freeA(n - 1); rel = false; waitA(n); }
      };
      auto freeP = [&](int n) { mbar_arrive_if(rel, bars + 8 * (B_EA + rslot(n - 1))); };
      auto ffn_step = [&](auto first, auto split, float (&acc)[64], int n, int kb, auto done, auto work) {
        constexpr int SPLIT = decltype(split)::value;
        acquire(n);
        wg_fence();
        const uint64_t dx = d128(dX + kb * 1024), db = d128(dN + RING + rslot(n) * 1024);
        mma_ss128<0, 1, decltype(first)::value>(acc, dx, db, kb);
#pragma unroll
        for (int k = 1; k < SPLIT; k++) mma_ss128<0, 1, 1>(acc, dx + k * 2, db + k * 128);
        wg_commit();
        work();
        wg_wait<1>();
        freeP(n);
        done();
        if (SPLIT < 4) {
          wg_fence();
#pragma unroll
          for (int k = SPLIT; k < 4; k++) mma_ss128<0, 1, 1>(acc, dx + k * 2, db + k * 128);
          wg_commit();
        }
      };
      {
        const int s0 = 2 * rb + wg, kr = 2 * ((s0 & 1) | ((s0 & 4) >> 1));
        const int m = lane >> 3, r = lane & 7;
        const uint32_t a0 = sb + OFF_XB + wg * 8192 + (((w >> 1) * 8 + (m >> 1)) * 2 + (w & 1)) * 256 + (m & 1) * 128 + ((r ^ (kr + (m & 1))) << 4);
        ffn_step(IC<1>(), IC<4>(), cA, 5, 4, [&] { fence_regs<0, 64>(cB); }, nop);
        asm volatile("bar.sync 5, 256;" ::: "memory");
        auto stage = [&](int i) {
          stsm4t(a0 + i * 1024, pack_bf16(cB[8 * i] - cB[34 + 8 * i], cB[8 * i + 1] - cB[35 + 8 * i]),
                 pack_bf16(cB[32 + 8 * i] + cB[8 * i + 2], cB[33 + 8 * i] + cB[8 * i + 3]),
                 pack_bf16(cB[8 * i + 4] - cB[38 + 8 * i], cB[8 * i + 5] - cB[39 + 8 * i]),
                 pack_bf16(cB[36 + 8 * i] + cB[8 * i + 6], cB[37 + 8 * i] + cB[8 * i + 7]));
          if (j == 0 && w == 0) {
            const uint32_t a1 = r ? sb + OFF_SP + 1024 : sb + OFF_SP + wg * 512 + (m & 1) * 256 + (m >> 1) * 128;
#pragma unroll
            for (int n = 2 * i; n < 2 * i + 2; n++)
              asm volatile("stmatrix.sync.aligned.m8n8.x4.shared.b16 [%0], {%1,%2,%3,%4};" ::"r"(a1 + ((n ^ (kr + (m >> 1)) ^ r) << 4)),
                           "r"(pack_bf16(cB[4 * n], cB[4 * n + 1])), "r"(pack_bf16(cB[4 * n + 2], cB[4 * n + 3])),
                           "r"(pack_bf16(cB[32 + 4 * n], cB[33 + 4 * n])), "r"(pack_bf16(cB[34 + 4 * n], cB[35 + 4 * n])) : "memory");
          }
        };
        auto publish = [&] {
          asm volatile("fence.proxy.async.shared::cta;" ::: "memory");
          __syncwarp();
          mbar_arrive_if(lane == 0, bars + 8 * (B_XS + wg));
          if (tid == 0) PROF_EV(3);
        };
        stage(0);
        ffn_step(IC<1>(), IC<FSPLIT>(), cA, 6, 5, nop, nop);
        stage(1);
        ffn_step(IC<1>(), IC<FSPLIT>(), cA, 7, 6, nop, nop);
        stage(2);
        ffn_step(IC<1>(), IC<2>(), cA, 8, 7, [&] { stage(3); }, nop);
        publish();
      }
      uint32_t gb0 = 0, gb1 = 0;
      uint32_t ob[2] = {0, 0};
      auto glu = [&](auto& acc, int half, int ho, int i0, int i1) {
#pragma unroll
        for (int i = i0; i < i1; i++)
          asm volatile("{\n.reg .b32 a, b;\ncvt.rn.relu.bf16x2.f32 a, %2, %1;\ncvt.rn.bf16x2.f32 b, %4, %3;\nmul.rn.bf16x2 a, a, b;\nmul.rn.bf16x2 %0, a, %5;\n}"
                       : "=r"(h[ho + i]) : "f"(acc[2 * i]), "f"(acc[2 * i + 1]), "f"(acc[half + 2 * i]), "f"(acc[half + 1 + 2 * i]), "r"(ob[i & 1]) : "memory");
      };
      ffn_step(IC<2>(), IC<1>(), cB, 9, zero, nop, nop);
#pragma unroll 1
      for (int kb = 1; kb < 8; kb++)
        ffn_step(IC<1>(), IC<FSPLIT>(), cB, 9 + kb, kb, nop, [&] {
          if (kb == GKB) {
            mbar_wait(bars + 8 * B_G, 0);
            asm volatile("ld.shared.u32 %0, [%2];\nld.shared.u32 %1, [%2+32];" : "=r"(gb0), "=r"(gb1) : "r"(sb + OFF_G + (wg * 64 + w * 16 + g) * 4) : "memory");
          } else if (kb == 5 + 2 * wg) {
            ob[0] = pack_bf16(1.0f - bf_hi(gb0), 1.0f - bf_hi(gb0)); ob[1] = pack_bf16(1.0f - bf_hi(gb1), 1.0f - bf_hi(gb1));
            glu(cA, 32, 0, 0, 16);
          }
        });
      const uint32_t tag = gb0 & 1;
      const float g0 = bf_hi(gb0), g1 = bf_hi(gb1);
      if (tid == 0) { PROF_EV(4); PROF_CK(43); }
      auto m_step = [&](auto first, int i) {
        acquire(17 + i);
        wg_fence();
        const uint64_t dx = d128(dX + i * 2048), dm = d64(dN + RING + rslot(17 + i) * 1024);
        mma_ss64<0, 1, decltype(first)::value>(ct, dx, dm);
#pragma unroll
        for (int k = 1; k < MSPLIT; k++) mma_ss64<0, 1, 1>(ct, dx + ((k >> 2) * 1024 + (k & 3) * 2), dm + k * 64);
        wg_commit();
        wg_wait<1>();
        freeP(17 + i);
        wg_fence();
#pragma unroll
        for (int k = MSPLIT; k < 8; k++) mma_ss64<0, 1, 1>(ct, dx + ((k >> 2) * 1024 + (k & 3) * 2), dm + k * 64);
        wg_commit();
      };
      m_step(IC<0>(), 0);
#pragma unroll 1
      for (int i = 1; i < 5; i++) {
        if (i == 1 + 2 * wg) glu(cB, 32, 16, 0, 16);
        if (i < 4) m_step(IC<1>(), i);
      }
      if (tid == 0) { PROF_EV(5); PROF_CK(44); }
      ffn_step(IC<0>(), IC<1>(), cC, 21, 0, nop, nop);
#pragma unroll 1
      for (int kb = 1; kb < 8; kb++)
        ffn_step(IC<1>(), IC<FSPLIT>(), cC, 21 + kb, kb, [&] { mbar_arrive_if(elect && !(kb & 1), bars + 8 * (B_ET + (kb >> 1) - 1)); }, [&] {
          if (kb == 1 + wg) glu(ct, 16, 48, 0, 8);
        });

      auto twait = [&](uint32_t bar, uint32_t par, int) { mbar_wait(bar, par); };
      const int fo = warp * 128 + lane;
      auto fetch = [&](uint4 (&pv)[4], int z) {
        twait(bars + 8 * (z < 4 ? B_Z + 2 * z + wg : z < 6 ? B_HP + z - 4 : B_HP + 2 + wg), 0, 8 + z);
        const uint8_t* src = smem + (z < 4 ? OFF_Z - z * U : z == 4 ? OFF_T : (z - 5) * U) + fo * 16;
#pragma unroll
        for (int i = 0; i < 4; i++) pv[i] = *(const uint4*)(src + i * 512);
      };
      const uint32_t peerZ = mapa(sb + OFF_Z + fo * 16, rank ^ 1), peerB = mapa(bars + 8 * (B_Z + wg), rank ^ 1);
      auto tile_mma = [&](auto off, int t, int k0, int k1, int init) {
        constexpr int O = decltype(off)::value;
        const uint64_t db = d128(dN + (t & 3) * (TB >> 4)), dw = db + rank * 256, dm = db + (rank ? 0 : 1536);
#pragma unroll
        for (int k = k0; k < k1; k++) {
          if (k == 0) mma_rs64<O, 1, 2>(ct, h[0], h[1], h[2], h[3], dw, init);
          else if (k < 14) mma_rs64<O, 1, 1>(ct, h[4 * k], h[4 * k + 1], h[4 * k + 2], h[4 * k + 3], k < 12 ? dw + k * 128 : dm + (k - 12) * 128);
          else mma_rs64<O, 1, 1>(ct, yf[4 * k - 56], yf[4 * k - 55], yf[4 * k - 54], yf[4 * k - 53], db + k * 128);
        }
      };
      uint4 pv[4] = {};
      auto tile = [&](auto off, int t) {
        constexpr int P = 32 - decltype(off)::value;
        const bool grid = t >= 4, pre = t >= 3 && t != 6;
        const int zo = grid ? t - 4 : t - 1, z = t - 3;
        const int owner = rb * 8 + 2 * ((q4 + zo + 1) & 3) + rank;
        uint4* dst = ws->part + (size_t)(owner * 3 + zo) * 1024 + fo;
        const uint32_t src = sb + OFF_Z - z * U + fo * 16;
        twait(bars + 8 * (B_FT + (t & 3)), t >> 2, t);
        wg_fence();
        tile_mma(off, t, 0, TH, zero);
        wg_commit();
        wg_wait<1>();
        mbar_arrive_if(elect && t < 6, bars + 8 * (B_ET + t - 1));
        if (t < 3) twait(bars + 8 * (t == 1 ? B_RD0 : B_RDY), 0, 14 + t);
        fence_regs<P, 32>(ct);
#pragma unroll
        for (int i = 0; i < 4; i++) {
          pv[i].x = (add_bf2(pv[i].x, pack_bf16(ct[P + 8 * i], ct[P + 8 * i + 1])) & ~(uint32_t)grid) | (tag & grid);
          pv[i].y = add_bf2(pv[i].y, pack_bf16(ct[P + 8 * i + 2], ct[P + 8 * i + 3]));
          pv[i].z = add_bf2(pv[i].z, pack_bf16(ct[P + 8 * i + 4], ct[P + 8 * i + 5]));
          pv[i].w = add_bf2(pv[i].w, pack_bf16(ct[P + 8 * i + 6], ct[P + 8 * i + 7]));
        }
        if (grid) {
#pragma unroll
          for (int i = 0; i < 4; i++)
            asm volatile("st.relaxed.gpu.global.v4.u32 [%0], {%1,%2,%3,%4};" ::"l"(dst + i * 32), "r"(pv[i].x), "r"(pv[i].y), "r"(pv[i].z), "r"(pv[i].w) : "memory");
          hint_add_if(lane == 0, &ws->cntP[32 * owner + 8 * (zo + (zo == 2 ? wg : 0))]);
        }
        auto share = [&](int i) {
          asm volatile("st.async.weak.shared::cluster.mbarrier::complete_tx::bytes.v4.b32 [%0], {%2,%3,%4,%5}, [%1];" ::"r"(peerZ - zo * U + i * 512),
                       "r"(peerB + 16 * zo), "r"(pv[i].x), "r"(pv[i].y), "r"(pv[i].z), "r"(pv[i].w) : "memory");
        };
#pragma unroll
        for (int i = 0; i < 4; i++) {
          if (!grid) share(i);
          wg_fence();
          tile_mma(off, t, TH + SPC * i, i < 3 ? TH + SPC * i + SPC : TL, 0);
        }
        wg_commit();
        if (pre) twait(bars + 8 * (B_Z + 2 * z + wg), 0, 8 + z);
        wg_fence();
#pragma unroll
        for (int i = 0; i < 4; i++) {
          asm volatile("{\n.reg .pred p;\nsetp.ne.b32 p, %5, 0;\nmov.b32 %0, 0;\nmov.b32 %1, 0;\nmov.b32 %2, 0;\nmov.b32 %3, 0;\n@p ld.shared.v4.u32 {%0,%1,%2,%3}, [%4];\n}"
                       : "=r"(pv[i].x), "=r"(pv[i].y), "=r"(pv[i].z), "=r"(pv[i].w) : "r"(src + i * 512), "r"((int)pre) : "memory");
          tile_mma(off, t, TL + i, i < 3 ? TL + 1 + i : 18, 0);
        }
        wg_commit();
      };
      asm volatile("barrier.cluster.wait.aligned;" ::: "memory");
      twait(bars + 8 * B_FT, 0, 0);
      wg_fence();
      tile_mma(IC<0>(), 0, 0, T0A, zero);
      wg_commit();
      waitA(29 + wg);
      wg_wait<1>();
      mbar_arrive_if(elect, bars + 8 * (B_ET + 3));
      glu(cC, 32, 32, 0, 16);
      if (tid == 0) PROF_EV(6);
      if (tid == 128) PROF_EV(27);
      mbar_wait(bars + 8 * (j == 0 ? B_T : B_TL), 0);
      if (tid == 0) { PROF_EV(7); PROF_CK(45); }
      wg_fence();
      {
        const uint64_t dt = d128(dN + (OFF_T >> 4) + wg * 512), de = d128(dK + RING + (1 + wg) * 1024);
        mma_ss64<0, 1, 0>(ci, de, dt);
        mma_ss64<32, 1, 0>(ci, de + 512, dt);
#pragma unroll
        for (int k = 1; k < 4; k++) {
          mma_ss64<0, 1, 1>(ci, de + k * 2, dt + k * 128);
          mma_ss64<32, 1, 1>(ci, de + (512 + k * 2), dt + k * 128);
        }
        wg_commit();
      }
      tile_mma(IC<0>(), 0, T0A, 14, 0);
      wg_commit();
      wg_wait<1>();
      if (elect) asm volatile("mbarrier.arrive.shared::cluster.b64 _, [%0];" ::"r"(mapa(bars + 8 * B_RDY, rank ^ 1)) : "memory");
      mbar_arrive_if(elect, bars + 8 * (B_PZ + 1));
      fence_regs<0, 64>(ci);
#pragma unroll
      for (int i = 0; i < 16; i++) {
        const float gg = ((i & 1) ? g1 : g0) * (2.0f / (2048.0f * 512.0f));
        if (i & 2) yf[i] = pack_pin((ci[2 * i] - ci[28 + 2 * i]) * gg, (ci[2 * i + 1] - ci[29 + 2 * i]) * gg);
        else yf[i] = pack_pin((ci[2 * i] + ci[36 + 2 * i]) * gg, (ci[2 * i + 1] + ci[37 + 2 * i]) * gg);
      }
      wg_fence();
      tile_mma(IC<0>(), 0, 14, 18, 0);
      wg_commit();
      if (tid == 0) PROF_EV(8);
      if (tid == 128) PROF_EV(28);
#pragma unroll 1
      for (int t = 1; t < 7; t += 2) {
        tile(IC<32>(), t);
        tile(IC<0>(), t + 1);
      }
      {
        uint4 p1[4], p2[4];
        auto acc4 = [&](uint4 (&d)[4], const uint4 (&a)[4]) {
#pragma unroll
          for (int i = 0; i < 4; i++) { d[i].x = add_bf2(d[i].x, a[i].x); d[i].y = add_bf2(d[i].y, a[i].y); d[i].z = add_bf2(d[i].z, a[i].z); d[i].w = add_bf2(d[i].w, a[i].w); }
        };
        auto add32 = [&](const uint4 (&a)[4]) {
#pragma unroll
          for (int i = 0; i < 4; i++) {
            const uint32_t u[4] = {a[i].x, a[i].y, a[i].z, a[i].w};
#pragma unroll
            for (int e = 0; e < 4; e++) { ct[32 + 8 * i + 2 * e] += bf_lo(u[e]); ct[33 + 8 * i + 2 * e] += bf_hi(u[e]); }
          }
        };
        twait(bars + 8 * (B_FT + 3), 1, 7);
        wg_fence();
        tile_mma(IC<32>(), 7, 0, TH, zero);
        wg_commit();
        wg_wait<1>();
        fence_regs<0, 32>(ct);
#pragma unroll
        for (int i = 0; i < 4; i++)
          asm volatile("st.async.weak.shared::cluster.mbarrier::complete_tx::bytes.v4.b32 [%0], {%2,%3,%4,%5}, [%1];" ::"r"(peerZ - 3 * U + i * 512), "r"(peerB + 48),
                       "r"(pack_bf16(ct[8 * i], ct[8 * i + 1])), "r"(pack_bf16(ct[8 * i + 2], ct[8 * i + 3])), "r"(pack_bf16(ct[8 * i + 4], ct[8 * i + 5])),
                       "r"(pack_bf16(ct[8 * i + 6], ct[8 * i + 7])) : "memory");
        wg_fence();
        tile_mma(IC<32>(), 7, TH, 9, 0);
        wg_commit();
        fetch(pv, 4);
        fetch(p1, 5);
        wg_fence();
        tile_mma(IC<32>(), 7, 9, 14, 0);
        wg_commit();
        uint32_t bad = 0;
#pragma unroll
        for (int i = 0; i < 4; i++) { bad |= (pv[i].x ^ tag) | (p1[i].x ^ tag); pv[i].x &= ~1u; p1[i].x &= ~1u; }
        acc4(pv, p1);
        fetch(p1, 3);
        wg_fence();
        tile_mma(IC<32>(), 7, 14, 18, 0);
        wg_commit();
        if (tid == 0) { PROF_EV(9); PROF_CK(46); }
        if (tid == 128) PROF_EV(29);
        acc4(pv, p1);
        wg_wait<0>();
        fence_regs<32, 32>(ct);
        float sum[32];
#pragma unroll
        for (int i = 0; i < 4; i++) {
          const uint32_t u[4] = {pv[i].x, pv[i].y, pv[i].z, pv[i].w};
#pragma unroll
          for (int e = 0; e < 4; e++) { sum[8 * i + 2 * e] = ct[32 + 8 * i + 2 * e] + bf_lo(u[e]); sum[8 * i + 2 * e + 1] = ct[33 + 8 * i + 2 * e] + bf_hi(u[e]); }
        }
        fence_regs<0, 32>(sum);
        fetch(p2, 6);
        if (tid == 0) PROF_EV(24);
#pragma unroll
        for (int i = 0; i < 4; i++) bad |= p2[i].x ^ tag;
        if (__any_sync(0xffffffffu, bad & 1)) {
          const uint4* src = ws->part + (size_t)(rb * 8 + j) * 3 * 1024 + fo;
          uint4 p0[4];
          int n = 0;
          do {
            bad = 0;
#pragma unroll
            for (int i = 0; i < 4; i++) {
              pv[i] = ld_x4(src + i * 32); p0[i] = ld_x4(src + 1024 + i * 32); p2[i] = ld_x4(src + 2048 + i * 32);
              bad |= (pv[i].x ^ tag) | (p0[i].x ^ tag) | (p2[i].x ^ tag);
            }
            if (++n > (1 << 21)) __trap();
          } while (__any_sync(0xffffffffu, bad & 1));
#pragma unroll
          for (int i = 0; i < 4; i++) { pv[i].x &= ~1u; p0[i].x &= ~1u; }
          acc4(pv, p0);
          acc4(pv, p1); add32(pv);
#pragma unroll
          for (int i = 0; i < 32; i++) sum[i] = ct[32 + i];
        }
#pragma unroll
        for (int i = 0; i < 4; i++) p2[i].x &= ~1u;
#pragma unroll
        for (int i = 0; i < 32; i++) ct[32 + i] = sum[i];
        add32(p2);
#pragma unroll
        for (int i = 0; i < 4; i++)
          pv[i] = make_uint4(pack_bf16(ct[32 + 8 * i], ct[33 + 8 * i]), pack_bf16(ct[34 + 8 * i], ct[35 + 8 * i]), pack_bf16(ct[36 + 8 * i], ct[37 + 8 * i]), pack_bf16(ct[38 + 8 * i], ct[39 + 8 * i]));
        if (tid == 0) PROF_EV(14);
        const uint32_t stg = sb + OFF_T + warp * 2048;
        const int mr = (lane & 7) + ((lane >> 3) & 1) * 8, mc = lane >> 4;
#pragma unroll
        for (int i = 0; i < 4; i++)
          asm volatile("stmatrix.sync.aligned.m8n8.x4.shared.b16 [%0], {%1,%2,%3,%4};" ::"r"(stg + mr * 128 + (((2 * i + mc) ^ (mr & 7)) << 4)), "r"(pv[i].x),
                       "r"(pv[i].y), "r"(pv[i].z), "r"(pv[i].w) : "memory");
        __syncwarp();
#pragma unroll
        for (int i = 0; i < 4; i++) {
          const int r = 4 * i + (lane >> 3), c = lane & 7;
          const uint4 v = *(const uint4*)(smem + OFF_T + warp * 2048 + r * 128 + ((c ^ (r & 7)) << 4));
          *(uint4*)(out + (size_t)(2 * rb + wg + 32 * (16 * w + r)) * 512 + 64 * j + 8 * c) = v;
        }
      }
      if (tid == 0) { PROF_EV(15); PROF_CK(41); }
      if (tid == 128) PROF_EV(30);
    }
  } else if (warp < 12) {
    asm volatile("setmaxnreg.dec.sync.aligned.u32 104;");
    asm volatile("barrier.cluster.arrive.relaxed.aligned;" ::: "memory");
    const int t = tid - 256, w = warp - 8;
    const uint32_t ep = ld_x1(&ws->epoch[blockIdx.x * 8]);
    const uint32_t tag = (ep + 1) & 1;
    auto w_issue = [&](const CUtensorMap* m) {

      if (elect_one()) { mbar_expect_tx(bars + 8 * (B_WR + w), 3072); tma4d(sb + OFF_T + w * 3072, m, bars + 8 * (B_WR + w), 16 * kg, 0, 2 * w, tn); }

          __syncwarp();
    };
    auto gate_rows = [&] {
      const int r = 16 * j + 4 * w + (lane >> 3);
      const uint4* pg = (const uint4*)gate_w + (lane & 7);
      {
        float a = 0.f;
        asm volatile("bar.sync 4, 256;" ::: "memory");
#pragma unroll 1
        for (int hf = 0; hf < 2; hf++) {
          uint4 v[4], u[4];
#pragma unroll
          for (int kb = 0; kb < 4; kb++) v[kb] = __ldg(pg + (4 * hf + kb) * 8);
          mbar_wait(bars + 8 * (B_FE + 1 + 2 * hf), 0);
          if (hf) w_issue(&maps.wr);
#pragma unroll
          for (int kb = 0; kb < 4; kb++) u[kb] = *(const uint4*)(smem + (4 * hf + kb) * U + r * 128 + (((lane ^ r) & 7) << 4));
#pragma unroll
          for (int kb = 0; kb < 4; kb++) {
            const uint32_t uu[4] = {u[kb].x, u[kb].y, u[kb].z, u[kb].w}, vv[4] = {v[kb].x, v[kb].y, v[kb].z, v[kb].w};
#pragma unroll
            for (int e = 0; e < 4; e++) {
              uint32_t pr;
              asm("mul.rn.bf16x2 %0, %1, %2;" : "=r"(pr) : "r"(uu[e]), "r"(vv[e]));
              a += bf_lo(pr) + bf_hi(pr);
            }
          }
        }
#pragma unroll
        for (int o = 4; o; o >>= 1) a += __shfl_xor_sync(0xffffffffu, a, o);
        if ((lane & 7) == 0)
          asm volatile("st.relaxed.gpu.global.u32 [%0], %1;" ::"l"(ws->gate + rb * 128 + r),
                       "r"(pack_bf16(0.f, __fdividef(1.0f, 1.0f + __expf(-bf_lo(pack_bf16(a, 0.f))))) | tag) : "memory");
        if (t == 0) PROF_EV(18);
      }
    };
    {
      const int g = lane >> 2, q = lane & 3;
      uint32_t wf[32];
      if (!helper) {
        gate_rows();
        const uint32_t wa = sb + OFF_T + w * (3072 + 4) + q * 48 + g * 2;
#pragma unroll 1
        for (int ri = 0; ri < 2; ri++) {
          mbar_wait(bars + 8 * (B_WR + w), ri);
#pragma unroll
          for (int n2 = 0; n2 < 32 / WB; n2++) {
            uint32_t v[WB];
#pragma unroll
            for (int i = 0; i < WB; i++) {
              const int e = n2 * WB + i;
              asm volatile("ld.shared.u16 %0, [%1];" : "=r"(v[i]) : "r"(wa + ((e >> 1) & 7) * 192 + (e & 1) * (1536 + 2) + (e >> 4) * 16) : "memory");
            }
#pragma unroll
            for (int i = 0; i < WB; i++) wf[n2 * WB + i] = __byte_perm(wf[n2 * WB + i], v[i], 0x5432);
            if (WSLEEP) { asm volatile("nanosleep.u32 %0;" ::"r"(WSLEEP + (v[WB - 1] >> 16)) : "memory"); }
          }
          __syncwarp();
          if (ri == 0) w_issue(&maps.wi);
        }
        asm volatile("bar.sync 1, 128;" ::: "memory");
        if (t == 0) PROF_EV(11);
      } else {
        asm volatile("bar.sync 4, 256;" ::: "memory");
        hint_wait(&ws->cntW[0], (ep + 1) * 128u);
        const uint32_t t0 = (uint32_t)clock();
#pragma unroll 1
        for (;;) {
          uint32_t bad = 0;
#pragma unroll
          for (int i = 0; i < 32; i++) {
            const float2 v = ld_x2((const float2*)ws->Wh + (i >> 4) * 2048 + 16 * w + g + 8 * (i & 1) + 64 * q + ((i >> 1) & 7) * 256);
            wf[i] = __float_as_uint(v.x); bad |= __float_as_uint(v.y) ^ tag;
          }
          if (!__any_sync(0xffffffffu, bad & 1)) break;
          spin_guard(t0);
        }
        if (t == 0) PROF_EV(11);
      }
      if (w == 0 && elect_one()) { mbar_expect_tx(bars + 8 * B_W, 8192); bulk_load(sb + OFF_D, dtab, 8192, bars + 8 * B_W); }
      asm volatile("barrier.cluster.wait.aligned;" ::: "memory");
      mbar_wait(bars + 8 * B_W, 0);
      mbar_wait(bars + 8 * B_HX, 0);
      if (t == 0) PROF_EV(12);
      const uint32_t dd = (sb & 0x3FFFF) >> 4;
      const uint64_t dF = d128((dd + (OFF_D >> 4)) | (512u << 16)), dI = d128((dd + (OFF_D >> 4)) | (1u << 16)), dA = d128((dd + (OFF_XB >> 4)) | (512u << 16));
      float az[32];
      const int zero = blockIdx.x >> 16;
      uint32_t pf[32];
#pragma unroll
      for (int mt = 0; mt < 2; mt++) {
        wg_fence();
        if (mt == 0) mma_ss64<0, 3, 0>(az, dA, dF);
        else mma_ss64<0, 3, 2>(az, dA + 512, dF, zero);
#pragma unroll
        for (int k = 1; k < 4; k++) mma_ss64<0, 3, 1>(az, dA + (mt * 512 + k * 128), dF + k * 128);
        wg_commit();
        wg_wait<0>();
        fence_regs<0, 32>(az);
#pragma unroll
        for (int i = 0; i < 16; i++) {
          const float wr = bf_lo(wf[16 * mt + i]), wi = bf_hi(wf[16 * mt + i]);
          pf[16 * mt + i] = pack_pin(fmaf(az[2 * i], wr, -az[2 * i + 1] * wi), fmaf(az[2 * i], wi, az[2 * i + 1] * wr));
        }
      }
      if (t == 0) PROF_EV(16);
      {
        const int m = lane >> 3, r = lane & 7;
        const int sl = 2 * (m >> 1) + ((r >> 1) & 1) + 4 * (r >> 2);
        const uint32_t a0 = sb + OFF_XB + (2 * w + (m & 1)) * 2048 + sl * 64;
        uint32_t pk[16];
#pragma unroll
        for (int mt = 0; mt < 3; mt++) {
          if (mt < 2) {
            wg_fence();
            mma_rs64<0, 0, 2>(az, pf[16 * mt], pf[16 * mt + 1], pf[16 * mt + 2], pf[16 * mt + 3], dI, mt ? (int)helper : zero);
#pragma unroll
            for (int k = 1; k < 4; k++) mma_rs64<0, 0, 1>(az, pf[16 * mt + 4 * k], pf[16 * mt + 4 * k + 1], pf[16 * mt + 4 * k + 2], pf[16 * mt + 4 * k + 3], dI + k * 2);
            wg_commit();
          }
          if (mt > 0 && !helper) {
#pragma unroll
            for (int i = 0; i < 4; i++) stsm4t(a0 + ((((mt - 1) * 2 + (r & 1)) ^ (sl >> 1)) << 4) + i * 512, pk[4 * i], pk[4 * i + 1], pk[4 * i + 2], pk[4 * i + 3]);
          }
          if (mt < 2) {
            wg_wait<0>();
            fence_regs<0, 32>(az);
#pragma unroll
            for (int i = 0; i < 16; i++) pk[i] = pack_pin(az[2 * i], az[2 * i + 1]);
          }
        }
      }
      if (helper) {
#pragma unroll
        for (int i = 0; i < 16; i++) {
          const int n = i >> 1, s0 = 8 * (n >> 1) + 2 * (n & 1) + (q & 1) + 4 * (q >> 1);
          if ((n & 1) == (int)(blockIdx.x & 1)) st_u2(ws->Ts + s0 * 64 + 16 * w + g + 8 * (i & 1), pack_bf16(az[2 * i], az[2 * i + 1]), tag);
        }
        __syncwarp();
        hint_add_if(lane == 0, &ws->cntH[0]);
        if (t == 0) { ws->epoch[blockIdx.x * 8] = ep + 1; PROF_EV(13); }
      } else {
        asm volatile("fence.proxy.async.shared::cta;" ::: "memory");
        __syncwarp();
        if (elect_one()) {
          if (t == 0) PROF_EV(17);
          if (SPACE) __nanosleep(SPACE * w);
          asm volatile("cp.async.bulk.tensor.3d.global.shared::cta.bulk_group [%0, {%2, %3, %4}], [%1];" ::"l"(&maps.ts), "r"(sb + OFF_XB + w * 4096),
                       "r"(32 * kg), "r"(0), "r"(8 * tn + 2 * w) : "memory");
          bulk_done_signal(&ws->cntT[32 * j]);
          asm volatile("mbarrier.arrive.shared::cluster.b64 _, [%0];" ::"r"(mapa(bars + 8 * B_RD0, rank ^ 1)) : "memory");
          if (t == 96) PROF_EV(13);
        }
        __syncwarp();
        if (j == 0) {
          hint_wait(&ws->cntH[0], (ep + 1) * 8u);
          const uint32_t t0 = (uint32_t)clock();
          float2 v;
          do { v = ld_x2((const float2*)ws->Ts + 2 * rb * 64 + t); spin_guard(t0); } while (__any_sync(0xffffffffu, (__float_as_uint(v.y) ^ tag) & 1));
          mbar_wait(bars + 8 * B_TL, 0);
          const uint32_t u = __float_as_uint(v.x);
          *(uint16_t*)(smem + OFF_T + t * 128 + ((t & 7) << 4)) = (uint16_t)u;
          *(uint16_t*)(smem + OFF_T + t * 128 + (((t & 7) ^ 1) << 4)) = (uint16_t)(u >> 16);
          asm volatile("fence.proxy.async.shared::cta;" ::: "memory");
          __syncwarp();
          mbar_arrive_if(lane == 0, bars + 8 * B_T);
        }
      }
    }
  } else {
    asm volatile("setmaxnreg.dec.sync.aligned.u32 24;");
    auto xf_load = [&](int q) {
      const uint32_t fb = bars + 8 * (B_FX + q);
      mbar_expect_tx(fb, U + 8192);
      tma3d(sb + q * U, &maps.x, fb, 64 * q, 0, 2 * rb);
      if (q >= 4) mbar_wait(bars + 8 * (B_FE + ((q - 4) >> 1)), 0);
      tma2d(sb + OFF_XB + (q & 3) * 8192, &maps.ft, fb, 64 * q, 64 * j);
    };
    if (elect_one()) {
      if (warp == 14) {
#pragma unroll
        for (int i = 0; i < B_FT; i++) mbar_init(bars + 8 * i, 1);
        asm volatile("fence.mbarrier_init.release.cluster;" ::: "memory");
        if (!helper) {
#pragma unroll 1
          for (int n = 0; n < 2; n++) {
            const uint32_t fb = bars + 8 * (B_FA + n);
            xf_load(2 * n); xf_load(2 * n + 1);
            mbar_expect_tx(fb, U);
            tma2d(sb + OFF_RING + n * U, &maps.g64, fb, f_full, 64 * n);
            tma2d(sb + OFF_RING + n * U + 8192, &maps.u64, fb, f_full, 64 * n);
          }
        }
      } else if (warp == 15) {
#pragma unroll
        for (int i = B_FT; i < NBAR; i++) mbar_init(bars + 8 * i, i < B_EA ? 1 : i < B_T ? 2 : 4);
#pragma unroll
        for (int i = 0; i < 8; i++) mbar_expect_tx(bars + 8 * (B_Z + i), U / 2);
        asm volatile("fence.mbarrier_init.release.cluster;" ::: "memory");
        asm volatile("fence.proxy.async.shared::cta;" ::: "memory");
      }
    }
    __syncwarp();
    asm volatile("bar.arrive 0, 384;" ::: "memory");
    asm volatile("bar.arrive 4, 256;" ::: "memory");
    __syncwarp();
    asm volatile("barrier.cluster.arrive.relaxed.aligned;" ::: "memory");
    asm volatile("bar.sync 3, 128;" ::: "memory");
    if (warp == 15 && !helper) {
        mbar_wait(bars + 8 * B_FE, 0);
        const uint32_t tag = (ld_x1(&ws->epoch[blockIdx.x * 8]) + 1) & 1;
        const int c = lane >> 4, jj = 16 * blockIdx.x + (lane & 15), jm = (2048 - jj) & 2047;
        const unsigned short* pr = (const unsigned short*)w_r + 256 * c;
        const unsigned short* pi = (const unsigned short*)w_i + 256 * c;
        const float wr = 0.25f * (bf_lo(__ldg(pr + jj * 257)) + bf_lo(__ldg(pr + jm * 257)));
        const float wi = 0.25f * (bf_lo(__ldg(pi + jj * 257)) - bf_lo(__ldg(pi + jm * 257)));
        st_u2(ws->Wh + c * 2048 + jj, c ? pack_bf16(-wi, wr) : pack_bf16(wr, wi), tag);
        __syncwarp();
        hint_add_if(lane == 0, &ws->cntW[0]);
        mbar_wait(bars + 8 * B_XS, 0);
        const uint32_t t0 = (uint32_t)clock();
        uint4 v;
        do { v = ld_x4(ws->gate + rb * 128 + 4 * lane); spin_guard(t0); } while (__any_sync(0xffffffffu, ((v.x ^ tag) | (v.y ^ tag) | (v.z ^ tag) | (v.w ^ tag)) & 1));
        *(uint4*)(smem + OFF_G + lane * 16) = v;
        __syncwarp();
        mbar_arrive_if(lane < 4, bars + 8 * B_G);
      }
    auto part_load = [&](int i, unsigned ep1) {
      const uint32_t bytes = i < 2 ? U : U / 2;
      mbar_wait(bars + 8 * (B_PZ + (i == 0)), 0);
      mbar_expect_tx(bars + 8 * (B_HP + i), bytes);
      flag_wait(&ws->cntP[32 * (rb * 8 + j) + 8 * i], ep1 * (i < 2 ? 8u : 4u));
      bulk_load(sb + (i == 0 ? OFF_T : i == 1 ? 0 : i * (U / 2)), ws->part + (size_t)(rb * 8 + j) * 3072 + (i < 2 ? i * 1024 : 1024 + i * 512), bytes, bars + 8 * (B_HP + i));
      if (i == 2) PROF_EV(26);
    };
    if ((!helper || warp == 15) && elect_one()) {
      if (warp < 14) {
        const int p = warp - 12;
#pragma unroll 1
        for (int i = 4 + p; i < 13; i += 2) asm volatile("prefetch.tensormap [%0];" ::"l"((const char*)&maps + i * 128) : "memory");
#pragma unroll 1
        for (int n = 2; n < 31; n++) {
          const bool table = n == 4 || n >= 29;
          const bool half = n >= 17 && n < 21;
          const int q = n < 4 ? n : n < 17 ? n - 1 : n - 5;
          const CUtensorMap* m = table ? &maps.e : half ? &maps.g32 + p : &maps.g64 + p;
          const int c0 = table ? 0 : half ? f_half : f_full + 64 * (q >> 3);
          const int c1 = table ? (2 * rb + ((n & 1) ^ 1)) * 128 + 64 * p : half ? 128 * (n - 17) : 64 * (q & 7);
          const uint32_t fb = bars + 8 * (B_FA + (n & 3)), dst = sb + OFF_RING + (n & 3) * U + p * 8192;
          if (n < 4) mbar_wait(bars + 8 * (B_FE + n - 2), 0);
          else mbar_wait(bars + 8 * (B_EA + (n & 3)), ((n >> 2) & 1) ^ 1);
          tma2d(dst, m, fb, c0, c1);
          if (p == 0) mbar_expect_tx(fb, U);
        }
        part_load(2 + p, ld_x1(&ws->epoch[blockIdx.x * 8]) + 1);
      } else if (warp == 15) {
        const unsigned ep1 = ld_x1(&ws->epoch[blockIdx.x * 8]) + 1;
        flag_wait(&ws->cntX[helper ? 0 : 32 * j], ep1 * 16u);
        PROF_EV(22);
        mbar_expect_tx(bars + 8 * B_HX, U);
        bulk_load(sb + OFF_XB, ws->X + (size_t)(helper ? 128 : kg * 8 + tn) * 8192, U, bars + 8 * B_HX);
        if (!helper) {
          flag_wait(&ws->cntT[32 * j], ep1 * 64u);
          PROF_EV(23);
          mbar_expect_tx(bars + 8 * B_TL, U);
          tma3d(sb + OFF_T, &maps.t, bars + 8 * B_TL, 64 * j, 0, 2 * rb);
          part_load(0, ep1); part_load(1, ep1);
          mbar_wait(bars + 8 * (B_HP + 2), 0); mbar_wait(bars + 8 * (B_HP + 3), 0);
          ws->epoch[blockIdx.x * 8] = ep1;
        }
      } else {
#pragma unroll 1
        for (int q = 4; q < 8; q++) xf_load(q);
        mbar_wait(bars + 8 * (B_FE + 2), 0);
        mbar_expect_tx(bars + 8 * B_E0, U);
        tma2d(sb + OFF_XB, &maps.e, bars + 8 * B_E0, 0, 2 * rb * 128);
        tma2d(sb + OFF_XB + 8192, &maps.e, bars + 8 * B_E0, 0, 2 * rb * 128 + 64);
#pragma unroll 1
        for (int h2 = 0; h2 < 2; h2++) {
          const int s0 = 2 * rb + h2, sg = (s0 & ~6) | ((s0 & 2) << 1) | ((s0 & 4) >> 1);
          mbar_wait(bars + 8 * (B_XS + h2), 0);
#pragma unroll 1
          for (int c = 0; c < 2; c++) {
            asm volatile("cp.async.bulk.tensor.4d.global.shared::cta.bulk_group [%0, {%2, %3, %4, %5}], [%1];" ::"l"(&maps.xs),
                         "r"(sb + OFF_XB + h2 * 8192 + c * 4096), "r"(0), "r"(sg), "r"(0), "r"(16 * j + 8 * c) : "memory");
            if (j == 0)
              asm volatile("cp.async.bulk.global.shared::cta.bulk_group [%0], [%1], 256;" ::"l"(ws->X + 128 * 8192 + c * 4096 + sg * 128),
                           "r"(sb + OFF_SP + h2 * 512 + c * 256) : "memory");
            if (SPACE && h2 + c < 2) __nanosleep(SPACE);
          }
        }
        bulk_done_signal(&ws->cntX[32 * j]);
        PROF_EV(20);
#pragma unroll 1
        for (int t = 0; t < 8; t++) {
          const int i = t < 3 ? t + 1 : t < 6 ? t - 2 : 0;
          const int col = 64 * (2 * ((q4 + i) & 3) + ((t < 3 || t == 6) ? 1 - rank : rank));
          const uint32_t fb = bars + 8 * (B_FT + (t & 3)), dst = sb + (t & 3) * TB;
          mbar_wait(bars + 8 * (B_ET + (t < 3 ? t + 1 : t & 3)), t >> 2);
          mbar_expect_tx(fb, TB);
          tma2d(dst, &maps.d224, fb, col, 224 * j);
          if (t < 2) mbar_wait(bars + 8 * (B_ET + t + 1), 0);
          tma2d(dst + 28672, &maps.ft, fb, col, 64 * j);
        }
      }
    }
  }
}

typedef CUresult (*EncodeFn)(CUtensorMap*, CUtensorMapDataType, cuuint32_t, void*, const cuuint64_t*, const cuuint64_t*, const cuuint32_t*,
                             const cuuint32_t*, CUtensorMapInterleave, CUtensorMapSwizzle, CUtensorMapL2promotion, CUtensorMapFloatOOBfill);

static void encode(EncodeFn f, CUtensorMap* m, const void* base, int rank, const cuuint64_t* dims, const cuuint64_t* strides, const cuuint32_t* box,
                   CUtensorMapSwizzle sw) {
  cuuint32_t es[5] = {1, 1, 1, 1, 1};
  f(m, CU_TENSOR_MAP_DATA_TYPE_BFLOAT16, rank, (void*)base, dims, strides, box, es, CU_TENSOR_MAP_INTERLEAVE_NONE, sw,
    CU_TENSOR_MAP_L2_PROMOTION_L2_128B, CU_TENSOR_MAP_FLOAT_OOB_FILL_NONE);
}

extern "C" void kernel_launch(void* const* d_in, const int* in_sizes, int n_in, void* d_out, int out_size) {
  (void)in_sizes; (void)n_in; (void)out_size;
  const __nv_bfloat16* x = (const __nv_bfloat16*)d_in[0];
  const __nv_bfloat16* w_r = (const __nv_bfloat16*)d_in[1];
  const __nv_bfloat16* w_i = (const __nv_bfloat16*)d_in[2];
  const __nv_bfloat16* Wg = (const __nv_bfloat16*)d_in[4];
  const __nv_bfloat16* Wu = (const __nv_bfloat16*)d_in[5];
  const __nv_bfloat16* Wd = (const __nv_bfloat16*)d_in[6];
  const __nv_bfloat16* gw = (const __nv_bfloat16*)d_in[7];

  void* fp = nullptr; cudaDriverEntryPointQueryResult qr;
  cudaGetDriverEntryPoint("cuTensorMapEncodeTiled", &fp, cudaEnableDefault, &qr);
  EncodeFn enc = (EncodeFn)fp;
  void *pFT, *pET, *pDT, *pW;
  cudaGetSymbolAddress(&pDT, g_DT); cudaGetSymbolAddress(&pW, g_work);
  void *pX = ((Work*)pW)->X, *pT = ((Work*)pW)->T;
  cudaGetSymbolAddress(&pFT, g_FT); cudaGetSymbolAddress(&pET, g_ET);

  Maps mp;
  const CUtensorMapSwizzle S128 = CU_TENSOR_MAP_SWIZZLE_128B, S64 = CU_TENSOR_MAP_SWIZZLE_64B;
  { cuuint64_t d[3] = {512, 64, 32}, s[2] = {32768, 1024}; cuuint32_t b[3] = {64, 64, 2}; encode(enc, &mp.x, x, 3, d, s, b, S128); }
  { cuuint64_t d[2] = {512, 512}, s[1] = {1024}; cuuint32_t b[2] = {64, 64}; encode(enc, &mp.ft, pFT, 2, d, s, b, S128); }
  { cuuint64_t d[4] = {128, 32, 2, 129}, s[3] = {256, 8192, 16384}; cuuint32_t b[4] = {128, 1, 2, 8}; encode(enc, &mp.xs, pX, 4, d, s, b, CU_TENSOR_MAP_SWIZZLE_NONE); }
  { cuuint64_t d[3] = {512, 32, 64}, s[2] = {65536, 1024}; cuuint32_t b[3] = {32, 32, 2}; encode(enc, &mp.ts, pT, 3, d, s, b, S64); }
  { cuuint64_t d[3] = {512, 64, 32}, s[2] = {1024, 65536}; cuuint32_t b[3] = {64, 64, 2}; encode(enc, &mp.t, pT, 3, d, s, b, S128); }
  { cuuint64_t d[2] = {64, 4096}, s[1] = {128}; cuuint32_t b[2] = {64, 64}; encode(enc, &mp.e, pET, 2, d, s, b, S128); }
  { cuuint64_t d[2] = {1792, 512}, s[1] = {3584}; cuuint32_t b[2] = {64, 64}, b2[2] = {32, 128};
    encode(enc, &mp.g64, Wg, 2, d, s, b, S128); encode(enc, &mp.u64, Wu, 2, d, s, b, S128);
    encode(enc, &mp.g32, Wg, 2, d, s, b2, S64); encode(enc, &mp.u32, Wu, 2, d, s, b2, S64); }
  { cuuint64_t d[2] = {512, 1792}, s[1] = {1024}; cuuint32_t b[2] = {64, 224}; encode(enc, &mp.d224, Wd, 2, d, s, b, S128); }
  { cuuint64_t d[4] = {264, 32, 8, 8}, s[3] = {32896, 512, 4112}; cuuint32_t b[4] = {24, 32, 2, 1};
    encode(enc, &mp.wr, w_r, 4, d, s, b, CU_TENSOR_MAP_SWIZZLE_NONE); encode(enc, &mp.wi, w_i, 4, d, s, b, CU_TENSOR_MAP_SWIZZLE_NONE); }

  cudaFuncSetAttribute(fused_kernel, cudaFuncAttributeMaxDynamicSharedMemorySize, SMEM_BYTES);
  fused_kernel<<<NCTA, 512, SMEM_BYTES>>>((Work*)pW, (const uint16_t*)pDT, w_r, w_i, gw, x, (__nv_bfloat16*)d_out, mp);
}
```

```cpp
#include <cuda_runtime.h>
#include <cuda_bf16.h>
#include <cuda.h>
#include <stdint.h>

namespace tbl {
constexpr double PI = 3.14159265358979323846264338327950288;
constexpr double sin_s(double x) { double t = x, s = x; for (int n = 1; n < 12; n++) { t *= -x * x / ((2 * n) * (2 * n + 1)); s += t; } return s; }
constexpr double cos_s(double x) { double t = 1, s = 1; for (int n = 1; n < 12; n++) { t *= -x * x / ((2 * n - 1) * (2 * n)); s += t; } return s; }
constexpr double cos2048(int m) {
  m &= 2047; if (m > 1024) m = 2048 - m;
  bool neg = false; if (m > 512) { m = 1024 - m; neg = true; }
  double v = (m <= 256) ? cos_s(2 * PI * m / 2048) : sin_s(2 * PI * (512 - m) / 2048);
  return neg ? -v : v;
}
constexpr uint16_t to_bf16(double v) {
  if (v == 0) return 0;
  uint16_t s = 0; if (v < 0) { s = 0x8000; v = -v; }
  int e = 0; while (v >= 2) { v /= 2; e++; } while (v < 1) { v *= 2; e--; }
  double m = (v - 1) * 128; int mi = (int)m; double fr = m - mi;
  if (fr > 0.5 || (fr == 0.5 && (mi & 1))) mi++;
  if (mi == 128) { mi = 0; e++; }
  return (uint16_t)(s | ((e + 127) << 7) | mi);
}
struct CosT { uint16_t v[2048]; constexpr CosT() : v() { for (int i = 0; i < 2048; i++) v[i] = to_bf16(cos2048(i)); } };
struct alignas(1024) FT {
  uint16_t v[512 * 512];
  constexpr FT() : v() {
    CosT c;
    for (int r = 0; r < 512; r++) {
      int k = (r >> 5) * 16 + 2 * (r & 7) + ((r >> 4) & 1), e = (r >> 3) & 1;
      int mul = 4 * k, add = e ? 512 : 0;
      if (k == 0 && e == 1) { mul = 1024; add = 0; }
      for (int d = 0; d < 512; d++) v[r * 512 + d] = c.v[(d * mul + add) & 2047];
    }
  }
};
struct alignas(1024) ET {
  uint16_t v[2048 * 128];
  constexpr ET() : v() {
    CosT c;
    for (int s = 0; s < 2048; s++)
      for (int j = 0; j < 64; j++) {
        const int o = (s & 31) * 8192 + (s >> 5) * 64 + j;
        v[o] = c.v[(s * j) & 2047]; v[o + 4096] = c.v[(s * j + 512) & 2047];
      }
  }
};
struct alignas(1024) DT {
  uint16_t v[64 * 64];
  constexpr DT() : v() {
    CosT c;
    for (int r = 0; r < 64; r++)
      for (int n = 0; n < 64; n++) {
        const int s0 = r >> 1, e = r & 1, f = n & 1;
        const int m = 64 * s0 * (n >> 1) + (e == f ? 0 : e ? -512 : 512);
        v[r * 64 + (((n >> 3) ^ (r & 7)) << 3) + (n & 7)] = c.v[m & 2047];
      }
  }
};
}

__device__ constexpr tbl::FT g_FT = tbl::FT();
__device__ constexpr tbl::ET g_ET = tbl::ET();
__device__ constexpr tbl::DT g_DT = tbl::DT();

struct alignas(1024) Work {
  unsigned epoch[132 * 8];
  unsigned cntX[8 * 32], cntT[8 * 32], cntP[128 * 32], cntW[32], cntH[32];
  alignas(16) float gate[16 * 128];
  alignas(16) uint2 Wh[2 * 2048];
  alignas(16) uint2 Ts[32 * 64];
  alignas(1024) uint16_t X[129 * 8192];
  alignas(1024) uint16_t T[32 * 64 * 512];
  alignas(1024) uint4 part[128 * 3 * 1024];
};
__device__ Work g_work;
#define PROF_EV(i) do {} while (0)
#define PROF_CK(i) do {} while (0)

__device__ __forceinline__ uint32_t smem_u32(const void* p) { return (uint32_t)__cvta_generic_to_shared(p); }
__device__ __forceinline__ void mbar_init(uint32_t bar, uint32_t cnt) { asm volatile("mbarrier.init.shared::cta.b64 [%0], %1;" ::"r"(bar), "r"(cnt)); }
__device__ __forceinline__ void mbar_expect_tx(uint32_t bar, uint32_t bytes) { asm volatile("mbarrier.arrive.expect_tx.shared::cta.b64 _, [%0], %1;" ::"r"(bar), "r"(bytes) : "memory"); }
__device__ __forceinline__ void mbar_arrive(uint32_t bar) { asm volatile("mbarrier.arrive.shared::cta.b64 _, [%0];" ::"r"(bar) : "memory"); }
__device__ __forceinline__ bool elect_one() {
  uint32_t p;
  asm volatile("{\n.reg .pred p;\nelect.sync _|p, 0xffffffff;\nselp.u32 %0, 1, 0, p;\n}" : "=r"(p));
  return p;
}
__device__ __forceinline__ void mbar_arrive_if(bool p, uint32_t bar) {
  asm volatile("{\n.reg .pred p;\nsetp.ne.b32 p, %1, 0;\n@p mbarrier.arrive.shared::cta.b64 _, [%0];\n}" ::"r"(bar), "r"((int)p) : "memory");
}
__device__ __forceinline__ void hint_add_if(bool p, unsigned* a) {
  asm volatile("{\n.reg .pred p;\nsetp.ne.b32 p, %1, 0;\n@p red.relaxed.gpu.global.add.u32 [%0], 1;\n}" ::"l"(a), "r"((int)p) : "memory");
}
__device__ __forceinline__ bool mbar_try(uint32_t bar, uint32_t parity) {
  uint32_t ok;
  asm volatile("{\n.reg .pred p;\nmbarrier.test_wait.parity.shared::cta.b64 p, [%1], %2;\nselp.u32 %0, 1, 0, p;\n}" : "=r"(ok) : "r"(bar), "r"(parity) : "memory");
  return ok;
}
__device__ __forceinline__ void mbar_wait(uint32_t bar, uint32_t parity) {
  asm volatile(
      "{\n.reg .pred p;\n.reg .u32 n;\nmov.u32 n, 0;\n"
      "W_LOOP:\nmbarrier.try_wait.parity.shared::cta.b64 p, [%0], %1;\n@p bra W_DONE;\n"
      "add.u32 n, n, 1;\nsetp.lt.u32 p, n, 0x40000;\n@p bra W_LOOP;\ntrap;\nW_DONE:\n}" ::"r"(bar), "r"(parity) : "memory");
}
__device__ __forceinline__ void bulk_load(uint32_t dst, const void* src, uint32_t bytes, uint32_t bar) {
  asm volatile("cp.async.bulk.shared::cluster.global.mbarrier::complete_tx::bytes [%0], [%1], %2, [%3];" ::"r"(dst), "l"(src), "r"(bytes), "r"(bar) : "memory");
}
__device__ __forceinline__ void spin_guard(uint32_t t0) { if ((uint32_t)clock() - t0 > (1u << 30)) __trap(); }
__device__ __forceinline__ float2 ld_x2(const float2* p) { float2 v; asm volatile("ld.relaxed.gpu.global.v2.f32 {%0,%1}, [%2];" : "=f"(v.x), "=f"(v.y) : "l"(p) : "memory"); return v; }
__device__ __forceinline__ void st_u2(uint2* p, uint32_t a, uint32_t b) { asm volatile("st.relaxed.gpu.global.v2.u32 [%0], {%1,%2};" ::"l"(p), "r"(a), "r"(b) : "memory"); }
__device__ __forceinline__ uint32_t ld_x1(const void* p) { uint32_t v; asm volatile("ld.relaxed.gpu.global.u32 %0, [%1];" : "=r"(v) : "l"(p) : "memory"); return v; }
__device__ __forceinline__ uint4 ld_x4(const void* p) { uint4 v; asm volatile("ld.relaxed.gpu.global.v4.u32 {%0,%1,%2,%3}, [%4];" : "=r"(v.x), "=r"(v.y), "=r"(v.z), "=r"(v.w) : "l"(p) : "memory"); return v; }
__device__ __forceinline__ uint32_t mapa(uint32_t a, uint32_t cta) { uint32_t r; asm volatile("mapa.shared::cluster.u32 %0, %1, %2;" : "=r"(r) : "r"(a), "r"(cta)); return r; }
__device__ __forceinline__ void stsm4t(uint32_t a, uint32_t r0, uint32_t r1, uint32_t r2, uint32_t r3) {
  asm volatile("stmatrix.sync.aligned.m8n8.x4.trans.shared.b16 [%0], {%1,%2,%3,%4};" ::"r"(a), "r"(r0), "r"(r1), "r"(r2), "r"(r3) : "memory");
}
__device__ __forceinline__ void hint_add(unsigned* p) { asm volatile("red.relaxed.gpu.global.add.u32 [%0], 1;" ::"l"(p) : "memory"); }
__device__ __forceinline__ void hint_wait(const unsigned* p, unsigned target) {
  const uint32_t t0 = (uint32_t)clock();
  while ((int)(ld_x1(p) - target) < 0) spin_guard(t0);
}
__device__ __forceinline__ void bulk_done_signal(unsigned* p) {
  asm volatile("cp.async.bulk.commit_group;\ncp.async.bulk.wait_group 0;\nfence.proxy.async.global;" ::: "memory");
  hint_add(p);
}
__device__ __forceinline__ void flag_wait(const unsigned* p, unsigned target) {
  hint_wait(p, target);
  asm volatile("fence.proxy.async.global;" ::: "memory");
}
__device__ __forceinline__ void tma2d(uint32_t dst, const CUtensorMap* m, uint32_t bar, int c0, int c1) {
  asm volatile("cp.async.bulk.tensor.2d.shared::cluster.global.mbarrier::complete_tx::bytes [%0], [%1, {%3, %4}], [%2];" ::"r"(dst), "l"(m), "r"(bar), "r"(c0), "r"(c1) : "memory");
}
__device__ __forceinline__ void tma3d(uint32_t dst, const CUtensorMap* m, uint32_t bar, int c0, int c1, int c2) {
  asm volatile("cp.async.bulk.tensor.3d.shared::cluster.global.mbarrier::complete_tx::bytes [%0], [%1, {%3, %4, %5}], [%2];" ::"r"(dst), "l"(m), "r"(bar), "r"(c0), "r"(c1), "r"(c2) : "memory");
}
__device__ __forceinline__ void tma4d(uint32_t dst, const CUtensorMap* m, uint32_t bar, int c0, int c1, int c2, int c3) {
  asm volatile("cp.async.bulk.tensor.4d.shared::cluster.global.mbarrier::complete_tx::bytes [%0], [%1, {%3, %4, %5, %6}], [%2];" ::"r"(dst), "l"(m), "r"(bar), "r"(c0), "r"(c1), "r"(c2), "r"(c3) : "memory");
}
__device__ __forceinline__ void wg_fence() { asm volatile("wgmma.fence.sync.aligned;" ::: "memory"); }
__device__ __forceinline__ void wg_commit() { asm volatile("wgmma.commit_group.sync.aligned;" ::: "memory"); }
template <int N> __device__ __forceinline__ void wg_wait() { asm volatile("wgmma.wait_group.sync.aligned %0;" ::"n"(N) : "memory"); }
template <int O, int N, int NN> __device__ __forceinline__ void fence_regs(float (&d)[NN]) {
#pragma unroll
  for (int i = 0; i < N; i++) asm volatile("" : "+f"(d[O + i])::"memory");
}
__device__ __forceinline__ uint32_t pack_bf16(float lo, float hi) {
  uint32_t r; asm("cvt.rn.bf16x2.f32 %0, %1, %2;" : "=r"(r) : "f"(hi), "f"(lo)); return r;
}
__device__ __forceinline__ uint32_t pack_pin(float lo, float hi) {
  uint32_t r; asm volatile("cvt.rn.bf16x2.f32 %0, %1, %2;" : "=r"(r) : "f"(hi), "f"(lo) : "memory"); return r;
}
__device__ __forceinline__ uint32_t add_bf2(uint32_t a, uint32_t b) { uint32_t r; asm("add.rn.bf16x2 %0, %1, %2;" : "=r"(r) : "r"(a), "r"(b)); return r; }
__device__ __forceinline__ float bf_lo(uint32_t u) { return __uint_as_float(u << 16); }
__device__ __forceinline__ float bf_hi(uint32_t u) { return __uint_as_float(u & 0xffff0000u); }

__device__ __forceinline__ uint64_t d128(uint32_t lo) { uint64_t d; asm("mov.b64 %0, {%1, 0x40000040};" : "=l"(d) : "r"(lo)); return d; }
__device__ __forceinline__ uint64_t d64(uint32_t lo) { uint64_t d; asm("mov.b64 %0, {%1, 0x80000020};" : "=l"(d) : "r"(lo)); return d; }
template<int O,int TB,int ACC,int NN> __device__ __forceinline__ void mma_ss64(float (&d)[NN], uint64_t da, uint64_t db, int sd = 0){
  if constexpr (ACC == 1) asm volatile("wgmma.mma_async.sync.aligned.m64n64k16.f32.bf16.bf16 {%0,%1,%2,%3,%4,%5,%6,%7,%8,%9,%10,%11,%12,%13,%14,%15,%16,%17,%18,%19,%20,%21,%22,%23,%24,%25,%26,%27,%28,%29,%30,%31}, %32, %33, 1, 1, 1, %35, %34;"
   : "+f"(d[O+0]), "+f"(d[O+1]), "+f"(d[O+2]), "+f"(d[O+3]), "+f"(d[O+4]), "+f"(d[O+5]), "+f"(d[O+6]), "+f"(d[O+7]), "+f"(d[O+8]), "+f"(d[O+9]), "+f"(d[O+10]), "+f"(d[O+11]), "+f"(d[O+12]), "+f"(d[O+13]), "+f"(d[O+14]), "+f"(d[O+15]), "+f"(d[O+16]), "+f"(d[O+17]), "+f"(d[O+18]), "+f"(d[O+19]), "+f"(d[O+20]), "+f"(d[O+21]), "+f"(d[O+22]), "+f"(d[O+23]), "+f"(d[O+24]), "+f"(d[O+25]), "+f"(d[O+26]), "+f"(d[O+27]), "+f"(d[O+28]), "+f"(d[O+29]), "+f"(d[O+30]), "+f"(d[O+31])
   : "l"(da), "l"(db), "n"(TB & 1), "n"(TB >> 1));
  else if constexpr (ACC == 0) asm volatile("wgmma.mma_async.sync.aligned.m64n64k16.f32.bf16.bf16 {%0,%1,%2,%3,%4,%5,%6,%7,%8,%9,%10,%11,%12,%13,%14,%15,%16,%17,%18,%19,%20,%21,%22,%23,%24,%25,%26,%27,%28,%29,%30,%31}, %32, %33, 0, 1, 1, %35, %34;"
   : "=f"(d[O+0]), "=f"(d[O+1]), "=f"(d[O+2]), "=f"(d[O+3]), "=f"(d[O+4]), "=f"(d[O+5]), "=f"(d[O+6]), "=f"(d[O+7]), "=f"(d[O+8]), "=f"(d[O+9]), "=f"(d[O+10]), "=f"(d[O+11]), "=f"(d[O+12]), "=f"(d[O+13]), "=f"(d[O+14]), "=f"(d[O+15]), "=f"(d[O+16]), "=f"(d[O+17]), "=f"(d[O+18]), "=f"(d[O+19]), "=f"(d[O+20]), "=f"(d[O+21]), "=f"(d[O+22]), "=f"(d[O+23]), "=f"(d[O+24]), "=f"(d[O+25]), "=f"(d[O+26]), "=f"(d[O+27]), "=f"(d[O+28]), "=f"(d[O+29]), "=f"(d[O+30]), "=f"(d[O+31])
   : "l"(da), "l"(db), "n"(TB & 1), "n"(TB >> 1));
  else asm volatile("{\n.reg .pred p;\nsetp.ne.b32 p, %36, 0;\nwgmma.mma_async.sync.aligned.m64n64k16.f32.bf16.bf16 {%0,%1,%2,%3,%4,%5,%6,%7,%8,%9,%10,%11,%12,%13,%14,%15,%16,%17,%18,%19,%20,%21,%22,%23,%24,%25,%26,%27,%28,%29,%30,%31}, %32, %33, p, 1, 1, %35, %34;\n}"
   : "+f"(d[O+0]), "+f"(d[O+1]), "+f"(d[O+2]), "+f"(d[O+3]), "+f"(d[O+4]), "+f"(d[O+5]), "+f"(d[O+6]), "+f"(d[O+7]), "+f"(d[O+8]), "+f"(d[O+9]), "+f"(d[O+10]), "+f"(d[O+11]), "+f"(d[O+12]), "+f"(d[O+13]), "+f"(d[O+14]), "+f"(d[O+15]), "+f"(d[O+16]), "+f"(d[O+17]), "+f"(d[O+18]), "+f"(d[O+19]), "+f"(d[O+20]), "+f"(d[O+21]), "+f"(d[O+22]), "+f"(d[O+23]), "+f"(d[O+24]), "+f"(d[O+25]), "+f"(d[O+26]), "+f"(d[O+27]), "+f"(d[O+28]), "+f"(d[O+29]), "+f"(d[O+30]), "+f"(d[O+31])
   : "l"(da), "l"(db), "n"(TB & 1), "n"(TB >> 1), "r"(sd));
}
template<int O,int TB,int ACC,int NN> __device__ __forceinline__ void mma_rs64(float (&d)[NN], uint32_t a0, uint32_t a1, uint32_t a2, uint32_t a3, uint64_t db, int sd = 0){
  if constexpr (ACC == 1) asm volatile("wgmma.mma_async.sync.aligned.m64n64k16.f32.bf16.bf16 {%0,%1,%2,%3,%4,%5,%6,%7,%8,%9,%10,%11,%12,%13,%14,%15,%16,%17,%18,%19,%20,%21,%22,%23,%24,%25,%26,%27,%28,%29,%30,%31}, {%32,%33,%34,%35}, %36, 1, 1, 1, %37;"
   : "+f"(d[O+0]), "+f"(d[O+1]), "+f"(d[O+2]), "+f"(d[O+3]), "+f"(d[O+4]), "+f"(d[O+5]), "+f"(d[O+6]), "+f"(d[O+7]), "+f"(d[O+8]), "+f"(d[O+9]), "+f"(d[O+10]), "+f"(d[O+11]), "+f"(d[O+12]), "+f"(d[O+13]), "+f"(d[O+14]), "+f"(d[O+15]), "+f"(d[O+16]), "+f"(d[O+17]), "+f"(d[O+18]), "+f"(d[O+19]), "+f"(d[O+20]), "+f"(d[O+21]), "+f"(d[O+22]), "+f"(d[O+23]), "+f"(d[O+24]), "+f"(d[O+25]), "+f"(d[O+26]), "+f"(d[O+27]), "+f"(d[O+28]), "+f"(d[O+29]), "+f"(d[O+30]), "+f"(d[O+31])
   : "r"(a0), "r"(a1), "r"(a2), "r"(a3), "l"(db), "n"(TB));
  else if constexpr (ACC == 0) asm volatile("wgmma.mma_async.sync.aligned.m64n64k16.f32.bf16.bf16 {%0,%1,%2,%3,%4,%5,%6,%7,%8,%9,%10,%11,%12,%13,%14,%15,%16,%17,%18,%19,%20,%21,%22,%23,%24,%25,%26,%27,%28,%29,%30,%31}, {%32,%33,%34,%35}, %36, 0, 1, 1, %37;"
   : "=f"(d[O+0]), "=f"(d[O+1]), "=f"(d[O+2]), "=f"(d[O+3]), "=f"(d[O+4]), "=f"(d[O+5]), "=f"(d[O+6]), "=f"(d[O+7]), "=f"(d[O+8]), "=f"(d[O+9]), "=f"(d[O+10]), "=f"(d[O+11]), "=f"(d[O+12]), "=f"(d[O+13]), "=f"(d[O+14]), "=f"(d[O+15]), "=f"(d[O+16]), "=f"(d[O+17]), "=f"(d[O+18]), "=f"(d[O+19]), "=f"(d[O+20]), "=f"(d[O+21]), "=f"(d[O+22]), "=f"(d[O+23]), "=f"(d[O+24]), "=f"(d[O+25]), "=f"(d[O+26]), "=f"(d[O+27]), "=f"(d[O+28]), "=f"(d[O+29]), "=f"(d[O+30]), "=f"(d[O+31])
   : "r"(a0), "r"(a1), "r"(a2), "r"(a3), "l"(db), "n"(TB));
  else asm volatile("{\n.reg .pred p;\nsetp.ne.b32 p, %38, 0;\nwgmma.mma_async.sync.aligned.m64n64k16.f32.bf16.bf16 {%0,%1,%2,%3,%4,%5,%6,%7,%8,%9,%10,%11,%12,%13,%14,%15,%16,%17,%18,%19,%20,%21,%22,%23,%24,%25,%26,%27,%28,%29,%30,%31}, {%32,%33,%34,%35}, %36, p, 1, 1, %37;\n}"
   : "+f"(d[O+0]), "+f"(d[O+1]), "+f"(d[O+2]), "+f"(d[O+3]), "+f"(d[O+4]), "+f"(d[O+5]), "+f"(d[O+6]), "+f"(d[O+7]), "+f"(d[O+8]), "+f"(d[O+9]), "+f"(d[O+10]), "+f"(d[O+11]), "+f"(d[O+12]), "+f"(d[O+13]), "+f"(d[O+14]), "+f"(d[O+15]), "+f"(d[O+16]), "+f"(d[O+17]), "+f"(d[O+18]), "+f"(d[O+19]), "+f"(d[O+20]), "+f"(d[O+21]), "+f"(d[O+22]), "+f"(d[O+23]), "+f"(d[O+24]), "+f"(d[O+25]), "+f"(d[O+26]), "+f"(d[O+27]), "+f"(d[O+28]), "+f"(d[O+29]), "+f"(d[O+30]), "+f"(d[O+31])
   : "r"(a0), "r"(a1), "r"(a2), "r"(a3), "l"(db), "n"(TB), "r"(sd));
}
template<int O,int TB,int ACC,int NN> __device__ __forceinline__ void mma_ss128(float (&d)[NN], uint64_t da, uint64_t db, int sd = 0){
  if constexpr (ACC == 1) asm volatile("wgmma.mma_async.sync.aligned.m64n128k16.f32.bf16.bf16 {%0,%1,%2,%3,%4,%5,%6,%7,%8,%9,%10,%11,%12,%13,%14,%15,%16,%17,%18,%19,%20,%21,%22,%23,%24,%25,%26,%27,%28,%29,%30,%31,%32,%33,%34,%35,%36,%37,%38,%39,%40,%41,%42,%43,%44,%45,%46,%47,%48,%49,%50,%51,%52,%53,%54,%55,%56,%57,%58,%59,%60,%61,%62,%63}, %64, %65, 1, 1, 1, %67, %66;"
   : "+f"(d[O+0]), "+f"(d[O+1]), "+f"(d[O+2]), "+f"(d[O+3]), "+f"(d[O+4]), "+f"(d[O+5]), "+f"(d[O+6]), "+f"(d[O+7]), "+f"(d[O+8]), "+f"(d[O+9]), "+f"(d[O+10]), "+f"(d[O+11]), "+f"(d[O+12]), "+f"(d[O+13]), "+f"(d[O+14]), "+f"(d[O+15]), "+f"(d[O+16]), "+f"(d[O+17]), "+f"(d[O+18]), "+f"(d[O+19]), "+f"(d[O+20]), "+f"(d[O+21]), "+f"(d[O+22]), "+f"(d[O+23]), "+f"(d[O+24]), "+f"(d[O+25]), "+f"(d[O+26]), "+f"(d[O+27]), "+f"(d[O+28]), "+f"(d[O+29]), "+f"(d[O+30]), "+f"(d[O+31]), "+f"(d[O+32]), "+f"(d[O+33]), "+f"(d[O+34]), "+f"(d[O+35]), "+f"(d[O+36]), "+f"(d[O+37]), "+f"(d[O+38]), "+f"(d[O+39]), "+f"(d[O+40]), "+f"(d[O+41]), "+f"(d[O+42]), "+f"(d[O+43]), "+f"(d[O+44]), "+f"(d[O+45]), "+f"(d[O+46]), "+f"(d[O+47]), "+f"(d[O+48]), "+f"(d[O+49]), "+f"(d[O+50]), "+f"(d[O+51]), "+f"(d[O+52]), "+f"(d[O+53]), "+f"(d[O+54]), "+f"(d[O+55]), "+f"(d[O+56]), "+f"(d[O+57]), "+f"(d[O+58]), "+f"(d[O+59]), "+f"(d[O+60]), "+f"(d[O+61]), "+f"(d[O+62]), "+f"(d[O+63])
   : "l"(da), "l"(db), "n"(TB & 1), "n"(TB >> 1));
  else if constexpr (ACC == 0) asm volatile("wgmma.mma_async.sync.aligned.m64n128k16.f32.bf16.bf16 {%0,%1,%2,%3,%4,%5,%6,%7,%8,%9,%10,%11,%12,%13,%14,%15,%16,%17,%18,%19,%20,%21,%22,%23,%24,%25,%26,%27,%28,%29,%30,%31,%32,%33,%34,%35,%36,%37,%38,%39,%40,%41,%42,%43,%44,%45,%46,%47,%48,%49,%50,%51,%52,%53,%54,%55,%56,%57,%58,%59,%60,%61,%62,%63}, %64, %65, 0, 1, 1, %67, %66;"
   : "=f"(d[O+0]), "=f"(d[O+1]), "=f"(d[O+2]), "=f"(d[O+3]), "=f"(d[O+4]), "=f"(d[O+5]), "=f"(d[O+6]), "=f"(d[O+7]), "=f"(d[O+8]), "=f"(d[O+9]), "=f"(d[O+10]), "=f"(d[O+11]), "=f"(d[O+12]), "=f"(d[O+13]), "=f"(d[O+14]), "=f"(d[O+15]), "=f"(d[O+16]), "=f"(d[O+17]), "=f"(d[O+18]), "=f"(d[O+19]), "=f"(d[O+20]), "=f"(d[O+21]), "=f"(d[O+22]), "=f"(d[O+23]), "=f"(d[O+24]), "=f"(d[O+25]), "=f"(d[O+26]), "=f"(d[O+27]), "=f"(d[O+28]), "=f"(d[O+29]), "=f"(d[O+30]), "=f"(d[O+31]), "=f"(d[O+32]), "=f"(d[O+33]), "=f"(d[O+34]), "=f"(d[O+35]), "=f"(d[O+36]), "=f"(d[O+37]), "=f"(d[O+38]), "=f"(d[O+39]), "=f"(d[O+40]), "=f"(d[O+41]), "=f"(d[O+42]), "=f"(d[O+43]), "=f"(d[O+44]), "=f"(d[O+45]), "=f"(d[O+46]), "=f"(d[O+47]), "=f"(d[O+48]), "=f"(d[O+49]), "=f"(d[O+50]), "=f"(d[O+51]), "=f"(d[O+52]), "=f"(d[O+53]), "=f"(d[O+54]), "=f"(d[O+55]), "=f"(d[O+56]), "=f"(d[O+57]), "=f"(d[O+58]), "=f"(d[O+59]), "=f"(d[O+60]), "=f"(d[O+61]), "=f"(d[O+62]), "=f"(d[O+63])
   : "l"(da), "l"(db), "n"(TB & 1), "n"(TB >> 1));
  else asm volatile("{\n.reg .pred p;\nsetp.ne.b32 p, %68, 0;\nwgmma.mma_async.sync.aligned.m64n128k16.f32.bf16.bf16 {%0,%1,%2,%3,%4,%5,%6,%7,%8,%9,%10,%11,%12,%13,%14,%15,%16,%17,%18,%19,%20,%21,%22,%23,%24,%25,%26,%27,%28,%29,%30,%31,%32,%33,%34,%35,%36,%37,%38,%39,%40,%41,%42,%43,%44,%45,%46,%47,%48,%49,%50,%51,%52,%53,%54,%55,%56,%57,%58,%59,%60,%61,%62,%63}, %64, %65, p, 1, 1, %67, %66;\n}"
   : "+f"(d[O+0]), "+f"(d[O+1]), "+f"(d[O+2]), "+f"(d[O+3]), "+f"(d[O+4]), "+f"(d[O+5]), "+f"(d[O+6]), "+f"(d[O+7]), "+f"(d[O+8]), "+f"(d[O+9]), "+f"(d[O+10]), "+f"(d[O+11]), "+f"(d[O+12]), "+f"(d[O+13]), "+f"(d[O+14]), "+f"(d[O+15]), "+f"(d[O+16]), "+f"(d[O+17]), "+f"(d[O+18]), "+f"(d[O+19]), "+f"(d[O+20]), "+f"(d[O+21]), "+f"(d[O+22]), "+f"(d[O+23]), "+f"(d[O+24]), "+f"(d[O+25]), "+f"(d[O+26]), "+f"(d[O+27]), "+f"(d[O+28]), "+f"(d[O+29]), "+f"(d[O+30]), "+f"(d[O+31]), "+f"(d[O+32]), "+f"(d[O+33]), "+f"(d[O+34]), "+f"(d[O+35]), "+f"(d[O+36]), "+f"(d[O+37]), "+f"(d[O+38]), "+f"(d[O+39]), "+f"(d[O+40]), "+f"(d[O+41]), "+f"(d[O+42]), "+f"(d[O+43]), "+f"(d[O+44]), "+f"(d[O+45]), "+f"(d[O+46]), "+f"(d[O+47]), "+f"(d[O+48]), "+f"(d[O+49]), "+f"(d[O+50]), "+f"(d[O+51]), "+f"(d[O+52]), "+f"(d[O+53]), "+f"(d[O+54]), "+f"(d[O+55]), "+f"(d[O+56]), "+f"(d[O+57]), "+f"(d[O+58]), "+f"(d[O+59]), "+f"(d[O+60]), "+f"(d[O+61]), "+f"(d[O+62]), "+f"(d[O+63])
   : "l"(da), "l"(db), "n"(TB & 1), "n"(TB >> 1), "r"(sd));
}
template<int O,int TB,int ACC,int NN> __device__ __forceinline__ void mma_rs128(float (&d)[NN], uint32_t a0, uint32_t a1, uint32_t a2, uint32_t a3, uint64_t db, int sd = 0){
  if constexpr (ACC == 1) asm volatile("wgmma.mma_async.sync.aligned.m64n128k16.f32.bf16.bf16 {%0,%1,%2,%3,%4,%5,%6,%7,%8,%9,%10,%11,%12,%13,%14,%15,%16,%17,%18,%19,%20,%21,%22,%23,%24,%25,%26,%27,%28,%29,%30,%31,%32,%33,%34,%35,%36,%37,%38,%39,%40,%41,%42,%43,%44,%45,%46,%47,%48,%49,%50,%51,%52,%53,%54,%55,%56,%57,%58,%59,%60,%61,%62,%63}, {%64,%65,%66,%67}, %68, 1, 1, 1, %69;"
   : "+f"(d[O+0]), "+f"(d[O+1]), "+f"(d[O+2]), "+f"(d[O+3]), "+f"(d[O+4]), "+f"(d[O+5]), "+f"(d[O+6]), "+f"(d[O+7]), "+f"(d[O+8]), "+f"(d[O+9]), "+f"(d[O+10]), "+f"(d[O+11]), "+f"(d[O+12]), "+f"(d[O+13]), "+f"(d[O+14]), "+f"(d[O+15]), "+f"(d[O+16]), "+f"(d[O+17]), "+f"(d[O+18]), "+f"(d[O+19]), "+f"(d[O+20]), "+f"(d[O+21]), "+f"(d[O+22]), "+f"(d[O+23]), "+f"(d[O+24]), "+f"(d[O+25]), "+f"(d[O+26]), "+f"(d[O+27]), "+f"(d[O+28]), "+f"(d[O+29]), "+f"(d[O+30]), "+f"(d[O+31]), "+f"(d[O+32]), "+f"(d[O+33]), "+f"(d[O+34]), "+f"(d[O+35]), "+f"(d[O+36]), "+f"(d[O+37]), "+f"(d[O+38]), "+f"(d[O+39]), "+f"(d[O+40]), "+f"(d[O+41]), "+f"(d[O+42]), "+f"(d[O+43]), "+f"(d[O+44]), "+f"(d[O+45]), "+f"(d[O+46]), "+f"(d[O+47]), "+f"(d[O+48]), "+f"(d[O+49]), "+f"(d[O+50]), "+f"(d[O+51]), "+f"(d[O+52]), "+f"(d[O+53]), "+f"(d[O+54]), "+f"(d[O+55]), "+f"(d[O+56]), "+f"(d[O+57]), "+f"(d[O+58]), "+f"(d[O+59]), "+f"(d[O+60]), "+f"(d[O+61]), "+f"(d[O+62]), "+f"(d[O+63])
   : "r"(a0), "r"(a1), "r"(a2), "r"(a3), "l"(db), "n"(TB));
  else if constexpr (ACC == 0) asm volatile("wgmma.mma_async.sync.aligned.m64n128k16.f32.bf16.bf16 {%0,%1,%2,%3,%4,%5,%6,%7,%8,%9,%10,%11,%12,%13,%14,%15,%16,%17,%18,%19,%20,%21,%22,%23,%24,%25,%26,%27,%28,%29,%30,%31,%32,%33,%34,%35,%36,%37,%38,%39,%40,%41,%42,%43,%44,%45,%46,%47,%48,%49,%50,%51,%52,%53,%54,%55,%56,%57,%58,%59,%60,%61,%62,%63}, {%64,%65,%66,%67}, %68, 0, 1, 1, %69;"
   : "=f"(d[O+0]), "=f"(d[O+1]), "=f"(d[O+2]), "=f"(d[O+3]), "=f"(d[O+4]), "=f"(d[O+5]), "=f"(d[O+6]), "=f"(d[O+7]), "=f"(d[O+8]), "=f"(d[O+9]), "=f"(d[O+10]), "=f"(d[O+11]), "=f"(d[O+12]), "=f"(d[O+13]), "=f"(d[O+14]), "=f"(d[O+15]), "=f"(d[O+16]), "=f"(d[O+17]), "=f"(d[O+18]), "=f"(d[O+19]), "=f"(d[O+20]), "=f"(d[O+21]), "=f"(d[O+22]), "=f"(d[O+23]), "=f"(d[O+24]), "=f"(d[O+25]), "=f"(d[O+26]), "=f"(d[O+27]), "=f"(d[O+28]), "=f"(d[O+29]), "=f"(d[O+30]), "=f"(d[O+31]), "=f"(d[O+32]), "=f"(d[O+33]), "=f"(d[O+34]), "=f"(d[O+35]), "=f"(d[O+36]), "=f"(d[O+37]), "=f"(d[O+38]), "=f"(d[O+39]), "=f"(d[O+40]), "=f"(d[O+41]), "=f"(d[O+42]), "=f"(d[O+43]), "=f"(d[O+44]), "=f"(d[O+45]), "=f"(d[O+46]), "=f"(d[O+47]), "=f"(d[O+48]), "=f"(d[O+49]), "=f"(d[O+50]), "=f"(d[O+51]), "=f"(d[O+52]), "=f"(d[O+53]), "=f"(d[O+54]), "=f"(d[O+55]), "=f"(d[O+56]), "=f"(d[O+57]), "=f"(d[O+58]), "=f"(d[O+59]), "=f"(d[O+60]), "=f"(d[O+61]), "=f"(d[O+62]), "=f"(d[O+63])
   : "r"(a0), "r"(a1), "r"(a2), "r"(a3), "l"(db), "n"(TB));
  else asm volatile("{\n.reg .pred p;\nsetp.ne.b32 p, %70, 0;\nwgmma.mma_async.sync.aligned.m64n128k16.f32.bf16.bf16 {%0,%1,%2,%3,%4,%5,%6,%7,%8,%9,%10,%11,%12,%13,%14,%15,%16,%17,%18,%19,%20,%21,%22,%23,%24,%25,%26,%27,%28,%29,%30,%31,%32,%33,%34,%35,%36,%37,%38,%39,%40,%41,%42,%43,%44,%45,%46,%47,%48,%49,%50,%51,%52,%53,%54,%55,%56,%57,%58,%59,%60,%61,%62,%63}, {%64,%65,%66,%67}, %68, p, 1, 1, %69;\n}"
   : "+f"(d[O+0]), "+f"(d[O+1]), "+f"(d[O+2]), "+f"(d[O+3]), "+f"(d[O+4]), "+f"(d[O+5]), "+f"(d[O+6]), "+f"(d[O+7]), "+f"(d[O+8]), "+f"(d[O+9]), "+f"(d[O+10]), "+f"(d[O+11]), "+f"(d[O+12]), "+f"(d[O+13]), "+f"(d[O+14]), "+f"(d[O+15]), "+f"(d[O+16]), "+f"(d[O+17]), "+f"(d[O+18]), "+f"(d[O+19]), "+f"(d[O+20]), "+f"(d[O+21]), "+f"(d[O+22]), "+f"(d[O+23]), "+f"(d[O+24]), "+f"(d[O+25]), "+f"(d[O+26]), "+f"(d[O+27]), "+f"(d[O+28]), "+f"(d[O+29]), "+f"(d[O+30]), "+f"(d[O+31]), "+f"(d[O+32]), "+f"(d[O+33]), "+f"(d[O+34]), "+f"(d[O+35]), "+f"(d[O+36]), "+f"(d[O+37]), "+f"(d[O+38]), "+f"(d[O+39]), "+f"(d[O+40]), "+f"(d[O+41]), "+f"(d[O+42]), "+f"(d[O+43]), "+f"(d[O+44]), "+f"(d[O+45]), "+f"(d[O+46]), "+f"(d[O+47]), "+f"(d[O+48]), "+f"(d[O+49]), "+f"(d[O+50]), "+f"(d[O+51]), "+f"(d[O+52]), "+f"(d[O+53]), "+f"(d[O+54]), "+f"(d[O+55]), "+f"(d[O+56]), "+f"(d[O+57]), "+f"(d[O+58]), "+f"(d[O+59]), "+f"(d[O+60]), "+f"(d[O+61]), "+f"(d[O+62]), "+f"(d[O+63])
   : "r"(a0), "r"(a1), "r"(a2), "r"(a3), "l"(db), "n"(TB), "r"(sd));
}

#define NEARLY 0
#define XAHEAD 3
#define HEADN 6
#define WBATCH 1
#define WB 8
#define WSLEEP 20
#define XSPREAD 4
#define NOSEND 0
#define MSPLIT 2
#define PFALL 1
#define L2PF 0
#define STAG 0
#define EPF 2
#define XNB 2
#define FNB 0
#define GNB 0
#define TH 4
#define PF0 4
#define FSPLIT 1
#define MGLU 1
#define SPC 2
#define TL 14
#define GKB 4
#define T0A 8
#define TGATE 1
#define ZLATE 0
#define EARLYADD 0
#define OA 2
#define OB 11
#define SPACE 100
#define WPF 1
#define WAFTER 7
#define WPACE 0
#define GATE_AT 4
#define TPACE 40
#define PFMODE 0
#define MAPMODE 1
template <int V> struct IC { static constexpr int value = V; };
struct Maps { CUtensorMap x, ft, g64, u64, e, wr, wi, xs, ts, t, g32, u32, d224, fg; };

constexpr int NCTA = 130;
constexpr int U = 16384;
constexpr int TB = 36864;
constexpr int OFF_RING = 8 * U, OFF_Z = 12 * U, OFF_XB = 12 * U, OFF_T = 13 * U, OFF_D = OFF_T;
constexpr int OFF_BAR = 14 * U, OFF_SP = OFF_BAR + 512, OFF_G = OFF_SP + 1024 + 128;
constexpr int SMEM_BYTES = OFF_G + 512;
constexpr int B_FX = 0, B_FA = 8, B_FT = 12, B_Z = 16, B_W = 24, B_HX = 25, B_TL = 26, B_HP = 27, B_WR = 31, B_E0 = 35;
constexpr int B_EA = 36, B_ET = 40, B_PZ = 44, B_RDY = 46, B_FE = 47;
constexpr int B_T = 51, B_XS = 52, B_G = 54, B_RD0 = 55, NBAR = 56;
__host__ __device__ constexpr int rslot(int n) { return n & 3; }
__host__ __device__ constexpr int rpar(int n) { return (n >> 2) & 1; }

__global__ void __cluster_dims__(2, 1, 1) __launch_bounds__(512, 1)
fused_kernel(Work* __restrict__ ws, const uint16_t* __restrict__ dtab, const __nv_bfloat16* __restrict__ w_r, const __nv_bfloat16* __restrict__ w_i,
             const __nv_bfloat16* __restrict__ gate_w, const __nv_bfloat16* __restrict__ x, __nv_bfloat16* __restrict__ out,
             const __grid_constant__ Maps maps) {
  extern __shared__ __align__(1024) uint8_t smem[];
  if (threadIdx.x < 32 && elect_one()) {
#pragma unroll
    for (int i = 0; i < PF0; i++) asm volatile("prefetch.tensormap [%0];" ::"l"((const char*)&maps + i * 128) : "memory");
  }
  const uint32_t sb = smem_u32(smem);
  const uint32_t bars = sb + OFF_BAR;
  const int tid = threadIdx.x, lane = tid & 31;
  const int warp = __shfl_sync(0xffffffffu, tid >> 5, 0);
  const bool helper = blockIdx.x >= 128;
  const int cl = (blockIdx.x >> 1) & 63, rank = blockIdx.x & 1;
  const int q4 = (cl & 1) | ((cl >> 2) & 2), rb = ((cl >> 1) & 3) | ((cl >> 4) << 2);
  const int j = 2 * q4 + rank;
  const int f_full = 448 * q4 + (rank ? 256 : 0);
  const int f_half = 448 * q4 + (rank ? 224 : 192);
  const int kg = 2 * j + (rb >> 3), tn = rb & 7;

  if (tid == 64) { PROF_EV(0); PROF_CK(40); }
  if (warp < 8) {
    if (!helper && tid < 32) {
      const int r = 16 * j + (tid & 15);
      asm volatile("prefetch.global.L2 [%0];" ::"l"(x + (size_t)(2 * rb + (r >> 6) + 32 * (r & 63)) * 512 + 64 * (tid >> 4)));
    }
    asm volatile("barrier.cluster.arrive.relaxed.aligned;" ::: "memory");
    asm volatile("setmaxnreg.inc.sync.aligned.u32 192;");
    if (!helper) {
      const int wg = warp >> 2, w = warp & 3, g = lane >> 2;
      const bool elect = (tid & 127) == 0;
      float cX[32], cA[64], cB[64], cC[64], ci[64], ct[64];
      const int zero = blockIdx.x >> 16;
      uint32_t h[56], yf[16];
      const uint32_t d0 = (sb & 0x3FFFF) >> 4;
      const uint32_t dK = d0 | (1u << 16), dN = d0 | (512u << 16);
      const uint32_t dX = dK + wg * 512;
      constexpr uint32_t RING = OFF_RING >> 4;
      auto waitA = [&](int n) { mbar_wait(bars + 8 * (B_FA + rslot(n)), rpar(n)); };
      auto freeA = [&](int n) { mbar_arrive_if(elect, bars + 8 * (B_EA + rslot(n))); };
      auto nop = [] {};

      asm volatile("bar.sync 0, 384;" ::: "memory");
#pragma unroll 1
      for (int i = 0; i < 4; i++) {
        const uint64_t dx = d128(dX + i * 2048), df = d128(dK + (OFF_XB >> 4) + (i & 1) * 1024);
        mbar_wait(bars + 8 * (B_FX + 2 * i), 0);
        wg_fence();
        mma_ss64<0, 0, 2>(cX, df, dx, i);
        mma_ss64<0, 0, 1>(cX, df + 2, dx + 2);
        wg_commit(); wg_wait<1>();
        mbar_arrive_if(elect && i, bars + 8 * (B_EA + rslot(i - 1)));
        mma_ss64<0, 0, 1>(cX, df + 4, dx + 4);
        mma_ss64<0, 0, 1>(cX, df + 6, dx + 6);
        if (i == 0 && tid == 0) PROF_EV(1);
        mbar_wait(bars + 8 * (B_FX + 2 * i + 1), 0);
        wg_fence();
#pragma unroll
        for (int k = 0; k < 4; k++) mma_ss64<0, 0, 1>(cX, df + (512 + k * 2), dx + (1024 + k * 2));
        wg_commit();
        waitA(i);
        wg_fence();
        const uint64_t da = d128(dX + i * 1024), db = d128(dN + RING + i * 1024);
        mma_ss128<0, 1, 2>(cA, da, db, i);
        wg_commit(); wg_wait<1>();
        mbar_arrive_if(elect, bars + 8 * (B_FE + i));
#pragma unroll
        for (int k = 1; k < 4; k++) mma_ss128<0, 1, 1>(cA, da + k * 2, db + k * 128);
        wg_commit();
      }
      fence_regs<0, 32>(cX);
#pragma unroll
      for (int e = 0; e < 16; e++) yf[e] = pack_pin(cX[2 * e], cX[2 * e + 1]);
      if (tid == 0) { PROF_EV(2); PROF_CK(42); }
      {
        waitA(4); mbar_wait(bars + 8 * B_E0, 0);
        const uint64_t de = d128(dN + (wg ? RING : OFF_XB >> 4));
        wg_fence();
        mma_rs128<0, 1, 0>(cB, yf[0], yf[1], yf[2], yf[3], de);
        wg_commit();
        wg_wait<1>();
        freeA(3);
#pragma unroll
        for (int k = 1; k < 4; k++) mma_rs128<0, 1, 1>(cB, yf[4 * k], yf[4 * k + 1], yf[4 * k + 2], yf[4 * k + 3], de + k * 128);
        wg_commit();
      }
      bool rel = false;
      auto acquire = [&](int n) {
        rel = elect;
        if (!mbar_try(bars + 8 * (B_FA + rslot(n)), rpar(n))) { wg_wait<0>(); freeA(n - 1); rel = false; waitA(n); }
      };
      auto freeP = [&](int n) { mbar_arrive_if(rel, bars + 8 * (B_EA + rslot(n - 1))); };
      auto ffn_step = [&](auto first, auto split, float (&acc)[64], int n, int kb, auto done, auto work) {
        constexpr int SPLIT = decltype(split)::value;
        acquire(n);
        wg_fence();
        const uint64_t dx = d128(dX + kb * 1024), db = d128(dN + RING + rslot(n) * 1024);
        mma_ss128<0, 1, decltype(first)::value>(acc, dx, db, kb);
#pragma unroll
        for (int k = 1; k < SPLIT; k++) mma_ss128<0, 1, 1>(acc, dx + k * 2, db + k * 128);
        wg_commit();
        work();
        wg_wait<1>();
        freeP(n);
        done();
        if (SPLIT < 4) {
          wg_fence();
#pragma unroll
          for (int k = SPLIT; k < 4; k++) mma_ss128<0, 1, 1>(acc, dx + k * 2, db + k * 128);
          wg_commit();
        }
      };
      {
        const int s0 = 2 * rb + wg, kr = 2 * (s0 & 3);
        const int m = lane >> 3, r = lane & 7;
        const uint32_t a0 = sb + OFF_XB + wg * 8192 + (((w >> 1) * 8 + (m >> 1)) * 2 + (w & 1)) * 256 + (m & 1) * 128 + ((r ^ (kr + (m & 1))) << 4);
        ffn_step(IC<1>(), IC<4>(), cA, 5, 4, [&] { fence_regs<0, 64>(cB); }, nop);
        asm volatile("bar.sync 5, 256;" ::: "memory");
        auto stage = [&](int i) {
          stsm4t(a0 + i * 1024, pack_bf16(cB[8 * i] - cB[34 + 8 * i], cB[8 * i + 1] - cB[35 + 8 * i]),
                 pack_bf16(cB[32 + 8 * i] + cB[8 * i + 2], cB[33 + 8 * i] + cB[8 * i + 3]),
                 pack_bf16(cB[8 * i + 4] - cB[38 + 8 * i], cB[8 * i + 5] - cB[39 + 8 * i]),
                 pack_bf16(cB[36 + 8 * i] + cB[8 * i + 6], cB[37 + 8 * i] + cB[8 * i + 7]));
          if (j == 0 && w == 0) {
            const uint32_t a1 = r ? sb + OFF_SP + 1024 : sb + OFF_SP + wg * 512 + (m & 1) * 256 + (m >> 1) * 128;
#pragma unroll
            for (int n = 2 * i; n < 2 * i + 2; n++)
              asm volatile("stmatrix.sync.aligned.m8n8.x4.shared.b16 [%0], {%1,%2,%3,%4};" ::"r"(a1 + ((n ^ (kr + (m >> 1)) ^ r) << 4)),
                           "r"(pack_bf16(cB[4 * n], cB[4 * n + 1])), "r"(pack_bf16(cB[4 * n + 2], cB[4 * n + 3])),
                           "r"(pack_bf16(cB[32 + 4 * n], cB[33 + 4 * n])), "r"(pack_bf16(cB[34 + 4 * n], cB[35 + 4 * n])) : "memory");
          }
        };
        auto publish = [&] {
          asm volatile("fence.proxy.async.shared::cta;" ::: "memory");
          __syncwarp();
          mbar_arrive_if(lane == 0, bars + 8 * (B_XS + wg));
          if (tid == 0) PROF_EV(3);
        };
        stage(0);
        ffn_step(IC<1>(), IC<FSPLIT>(), cA, 6, 5, nop, nop);
        stage(1);
        ffn_step(IC<1>(), IC<FSPLIT>(), cA, 7, 6, nop, nop);
        stage(2);
        ffn_step(IC<1>(), IC<2>(), cA, 8, 7, [&] { stage(3); }, nop);
        publish();
      }
      uint32_t gb0 = 0, gb1 = 0;
      uint32_t ob[2] = {0, 0};
      auto glu = [&](auto& acc, int half, int ho, int i0, int i1) {
#pragma unroll
        for (int i = i0; i < i1; i++)
          asm volatile("{\n.reg .b32 a, b;\ncvt.rn.relu.bf16x2.f32 a, %2, %1;\ncvt.rn.bf16x2.f32 b, %4, %3;\nmul.rn.bf16x2 a, a, b;\nmul.rn.bf16x2 %0, a, %5;\n}"
                       : "=r"(h[ho + i]) : "f"(acc[2 * i]), "f"(acc[2 * i + 1]), "f"(acc[half + 2 * i]), "f"(acc[half + 1 + 2 * i]), "r"(ob[i & 1]) : "memory");
      };
      ffn_step(IC<2>(), IC<1>(), cB, 9, zero, nop, nop);
#pragma unroll 1
      for (int kb = 1; kb < 8; kb++)
        ffn_step(IC<1>(), IC<FSPLIT>(), cB, 9 + kb, kb, nop, [&] {
          if (kb == GKB) {
            mbar_wait(bars + 8 * B_G, 0);
            asm volatile("ld.shared.u32 %0, [%2];\nld.shared.u32 %1, [%2+32];" : "=r"(gb0), "=r"(gb1) : "r"(sb + OFF_G + (wg * 64 + w * 16 + g) * 4) : "memory");
          } else if (kb == 5 + 2 * wg) {
            ob[0] = pack_bf16(1.0f - bf_hi(gb0), 1.0f - bf_hi(gb0)); ob[1] = pack_bf16(1.0f - bf_hi(gb1), 1.0f - bf_hi(gb1));
            glu(cA, 32, 0, 0, 16);
          }
        });
      const uint32_t tag = gb0 & 1;
      const float g0 = bf_hi(gb0), g1 = bf_hi(gb1);
      if (tid == 0) { PROF_EV(4); PROF_CK(43); }
      auto m_step = [&](auto first, int i) {
        acquire(17 + i);
        wg_fence();
        const uint64_t dx = d128(dX + i * 2048), dm = d64(dN + RING + rslot(17 + i) * 1024);
        mma_ss64<0, 1, decltype(first)::value>(ct, dx, dm);
#pragma unroll
        for (int k = 1; k < MSPLIT; k++) mma_ss64<0, 1, 1>(ct, dx + ((k >> 2) * 1024 + (k & 3) * 2), dm + k * 64);
        wg_commit();
        wg_wait<1>();
        freeP(17 + i);
        wg_fence();
#pragma unroll
        for (int k = MSPLIT; k < 8; k++) mma_ss64<0, 1, 1>(ct, dx + ((k >> 2) * 1024 + (k & 3) * 2), dm + k * 64);
        wg_commit();
      };
      m_step(IC<0>(), 0);
#pragma unroll 1
      for (int i = 1; i < 5; i++) {
        if (i == 1 + 2 * wg) glu(cB, 32, 16, 0, 16);
        if (i < 4) m_step(IC<1>(), i);
      }
      if (tid == 0) { PROF_EV(5); PROF_CK(44); }
      ffn_step(IC<0>(), IC<1>(), cC, 21, 0, nop, nop);
#pragma unroll 1
      for (int kb = 1; kb < 8; kb++)
        ffn_step(IC<1>(), IC<FSPLIT>(), cC, 21 + kb, kb, [&] { mbar_arrive_if(elect && !(kb & 1), bars + 8 * (B_ET + (kb >> 1) - 1)); }, [&] {
          if (kb == 1 + wg) glu(ct, 16, 48, 0, 8);
        });

      auto twait = [&](uint32_t bar, uint32_t par, int) { mbar_wait(bar, par); };
      const int fo = warp * 128 + lane;
      auto fetch = [&](uint4 (&pv)[4], int z) {
        twait(bars + 8 * (z < 4 ? B_Z + 2 * z + wg : z < 6 ? B_HP + z - 4 : B_HP + 2 + wg), 0, 8 + z);
        const uint8_t* src = smem + (z < 4 ? OFF_Z - z * U : z == 4 ? OFF_T : (z - 5) * U) + fo * 16;
#pragma unroll
        for (int i = 0; i < 4; i++) pv[i] = *(const uint4*)(src + i * 512);
      };
      const uint32_t peerZ = mapa(sb + OFF_Z + fo * 16, rank ^ 1), peerB = mapa(bars + 8 * (B_Z + wg), rank ^ 1);
      auto tile_mma = [&](auto off, int t, int k0, int k1) {
        constexpr int O = decltype(off)::value;
        const uint64_t db = d128(dN + (t & 3) * (TB >> 4)), dw = db + rank * 256, dm = db + (rank ? 0 : 1536);
#pragma unroll
        for (int k = k0; k < k1; k++) {
          if (k == 0 && O == 0) mma_rs64<O, 1, 2>(ct, h[0], h[1], h[2], h[3], dw, zero);
          else if (k < 14) mma_rs64<O, 1, 1>(ct, h[4 * k], h[4 * k + 1], h[4 * k + 2], h[4 * k + 3], k < 12 ? dw + k * 128 : dm + (k - 12) * 128);
          else if (k == 14) mma_rs64<O, 1, 2>(ct, yf[0], yf[1], yf[2], yf[3], db + k * 128, zero);
          else mma_rs64<O, 1, 1>(ct, yf[4 * k - 56], yf[4 * k - 55], yf[4 * k - 54], yf[4 * k - 53], db + k * 128);
        }
      };
      uint4 pv[4];
      const float sgn = rank ? -1.0f : 1.0f;
      auto odd_head = [&](int t) {
        twait(bars + 8 * (B_FT + (t & 3)), t >> 2, t);
        wg_fence();
        tile_mma(IC<32>(), t, 14, 18);
        wg_commit();
        if (t < 4) twait(bars + 8 * (t == 1 ? B_RD0 : B_RDY), 0, 14 + t);
        wg_wait<0>();
        mbar_arrive_if(elect && t < 6, bars + 8 * (B_ET + t - 1));
        fence_regs<0, 64>(ct);
#pragma unroll
        for (int i = 0; i < 4; i++) {
          uint32_t u[4];
#pragma unroll
          for (int e = 0; e < 4; e++) u[e] = pack_pin(fmaf(sgn, ct[32 + 8 * i + 2 * e], ct[8 * i + 2 * e]), fmaf(sgn, ct[33 + 8 * i + 2 * e], ct[8 * i + 2 * e + 1]));
          pv[i] = make_uint4(u[0], u[1], u[2], u[3]);
        }
        wg_fence();
        tile_mma(IC<32>(), t, 0, OA);
#pragma unroll
        for (int i = 0; i < 4; i++) {
          asm volatile("st.async.weak.shared::cluster.mbarrier::complete_tx::bytes.v4.b32 [%0], {%2,%3,%4,%5}, [%1];" ::"r"(peerZ - (t >> 1) * U + i * 512),
                       "r"(peerB + 16 * (t >> 1)), "r"(pv[i].x), "r"(pv[i].y), "r"(pv[i].z), "r"(pv[i].w) : "memory");
          tile_mma(IC<32>(), t, OA + i, OA + i + 1);
        }
        wg_commit();
      };
      asm volatile("barrier.cluster.wait.aligned;" ::: "memory");
      twait(bars + 8 * B_FT, 0, 0);
      wg_fence();
      tile_mma(IC<0>(), 0, 0, T0A);
      wg_commit();
      waitA(29 + wg);
      wg_wait<1>();
      mbar_arrive_if(elect, bars + 8 * (B_ET + 3));
      glu(cC, 32, 32, 0, 16);
      if (tid == 0) PROF_EV(6);
      if (tid == 128) PROF_EV(27);
      mbar_wait(bars + 8 * (j == 0 ? B_T : B_TL), 0);
      if (tid == 0) { PROF_EV(7); PROF_CK(45); }
      wg_fence();
      {
        const uint64_t dt = d128(dN + (OFF_T >> 4) + wg * 512), de = d128(dK + RING + (1 + wg) * 1024);
        mma_ss64<0, 1, 0>(ci, de, dt);
        mma_ss64<32, 1, 0>(ci, de + 512, dt);
#pragma unroll
        for (int k = 1; k < 4; k++) {
          mma_ss64<0, 1, 1>(ci, de + k * 2, dt + k * 128);
          mma_ss64<32, 1, 1>(ci, de + (512 + k * 2), dt + k * 128);
        }
        wg_commit();
      }
      tile_mma(IC<0>(), 0, T0A, 14);
      wg_commit();
      wg_wait<1>();
      if (elect) asm volatile("mbarrier.arrive.shared::cluster.b64 _, [%0];" ::"r"(mapa(bars + 8 * B_RDY, rank ^ 1)) : "memory");
      mbar_arrive_if(elect, bars + 8 * (B_PZ + 1));
      fence_regs<0, 64>(ci);
#pragma unroll
      for (int i = 0; i < 16; i++) {
        const float gg = ((i & 1) ? g1 : g0) * (2.0f / (2048.0f * 512.0f));
        if (i & 2) yf[i] = pack_pin((ci[2 * i] - ci[28 + 2 * i]) * gg, (ci[2 * i + 1] - ci[29 + 2 * i]) * gg);
        else yf[i] = pack_pin((ci[2 * i] + ci[36 + 2 * i]) * gg, (ci[2 * i + 1] + ci[37 + 2 * i]) * gg);
      }
      if (tid == 0) PROF_EV(8);
      if (tid == 128) PROF_EV(28);
#pragma unroll 1
      for (int t = 1; t < 7; t += 2) {
        odd_head(t);
        wg_fence();
        tile_mma(IC<32>(), t, OA + 4, OB);
        wg_commit();
        fetch(pv, t >> 1);
        wg_fence();
        tile_mma(IC<32>(), t, OB, 14);
        wg_commit();
        const int zo = t >> 1, owner = rb * 8 + 2 * ((q4 + zo + 1) & 3) + rank;
        uint4* dst = ws->part + (size_t)(owner * 3 + zo) * 1024 + fo;
        twait(bars + 8 * (B_FT + ((t + 1) & 3)), (t + 1) >> 2, t + 1);
        wg_fence();
        tile_mma(IC<0>(), t + 1, 0, TH);
        wg_commit();
        wg_wait<1>();
        mbar_arrive_if(elect && t < 5, bars + 8 * (B_ET + t));
        fence_regs<32, 32>(ct);
#pragma unroll
        for (int i = 0; i < 4; i++)
          asm volatile("st.relaxed.gpu.global.v4.u32 [%0], {%1,%2,%3,%4};" ::"l"(dst + i * 32),
                       "r"((add_bf2(pv[i].x, pack_bf16(ct[32 + 8 * i], ct[33 + 8 * i])) & ~1u) | tag), "r"(add_bf2(pv[i].y, pack_bf16(ct[34 + 8 * i], ct[35 + 8 * i]))),
                       "r"(add_bf2(pv[i].z, pack_bf16(ct[36 + 8 * i], ct[37 + 8 * i]))), "r"(add_bf2(pv[i].w, pack_bf16(ct[38 + 8 * i], ct[39 + 8 * i]))) : "memory");
        hint_add_if(lane == 0, &ws->cntP[32 * owner + 8 * (zo + (zo == 2 ? wg : 0))]);
        wg_fence();
        tile_mma(IC<0>(), t + 1, TH, 14);
        wg_commit();
      }
      {
        uint4 p1[4], p2[4];
        auto acc4 = [&](uint4 (&d)[4], const uint4 (&a)[4]) {
#pragma unroll
          for (int i = 0; i < 4; i++) { d[i].x = add_bf2(d[i].x, a[i].x); d[i].y = add_bf2(d[i].y, a[i].y); d[i].z = add_bf2(d[i].z, a[i].z); d[i].w = add_bf2(d[i].w, a[i].w); }
        };
        auto add32 = [&](const uint4 (&a)[4]) {
#pragma unroll
          for (int i = 0; i < 4; i++) {
            const uint32_t u[4] = {a[i].x, a[i].y, a[i].z, a[i].w};
#pragma unroll
            for (int e = 0; e < 4; e++) { ct[32 + 8 * i + 2 * e] += bf_lo(u[e]); ct[33 + 8 * i + 2 * e] += bf_hi(u[e]); }
          }
        };
        odd_head(7);
        fetch(pv, 4);
        fetch(p1, 5);
        wg_fence();
        tile_mma(IC<32>(), 7, OA + 4, OB);
        wg_commit();
        uint32_t bad = 0;
#pragma unroll
        for (int i = 0; i < 4; i++) { bad |= (pv[i].x ^ tag) | (p1[i].x ^ tag); pv[i].x &= ~1u; p1[i].x &= ~1u; }
        acc4(pv, p1);
        fetch(p1, 3);
        wg_fence();
        tile_mma(IC<32>(), 7, OB, 14);
        wg_commit();
        if (tid == 0) { PROF_EV(9); PROF_CK(46); }
        if (tid == 128) PROF_EV(29);
        fetch(p2, 6);
        if (tid == 0) PROF_EV(24);
        wg_wait<0>();
        fence_regs<32, 32>(ct);
#pragma unroll
        for (int i = 0; i < 4; i++) bad |= p2[i].x ^ tag;
        if (__any_sync(0xffffffffu, bad & 1)) {
          const uint4* src = ws->part + (size_t)(rb * 8 + j) * 3 * 1024 + fo;
          uint4 p0[4];
          int n = 0;
          do {
            bad = 0;
#pragma unroll
            for (int i = 0; i < 4; i++) {
              pv[i] = ld_x4(src + i * 32); p0[i] = ld_x4(src + 1024 + i * 32); p2[i] = ld_x4(src + 2048 + i * 32);
              bad |= (pv[i].x ^ tag) | (p0[i].x ^ tag) | (p2[i].x ^ tag);
            }
            if (++n > (1 << 21)) __trap();
          } while (__any_sync(0xffffffffu, bad & 1));
#pragma unroll
          for (int i = 0; i < 4; i++) { pv[i].x &= ~1u; p0[i].x &= ~1u; }
          acc4(pv, p0);
        }
#pragma unroll
        for (int i = 0; i < 4; i++) p2[i].x &= ~1u;
        acc4(p1, p2);
        add32(pv); add32(p1);
#pragma unroll
        for (int i = 0; i < 4; i++)
          pv[i] = make_uint4(pack_bf16(ct[32 + 8 * i], ct[33 + 8 * i]), pack_bf16(ct[34 + 8 * i], ct[35 + 8 * i]), pack_bf16(ct[36 + 8 * i], ct[37 + 8 * i]), pack_bf16(ct[38 + 8 * i], ct[39 + 8 * i]));
        if (tid == 0) PROF_EV(14);
        const uint32_t stg = sb + OFF_T + warp * 2048;
        const int mr = (lane & 7) + ((lane >> 3) & 1) * 8, mc = lane >> 4;
#pragma unroll
        for (int i = 0; i < 4; i++)
          asm volatile("stmatrix.sync.aligned.m8n8.x4.shared.b16 [%0], {%1,%2,%3,%4};" ::"r"(stg + mr * 128 + (((2 * i + mc) ^ (mr & 7)) << 4)), "r"(pv[i].x),
                       "r"(pv[i].y), "r"(pv[i].z), "r"(pv[i].w) : "memory");
        __syncwarp();
#pragma unroll
        for (int i = 0; i < 4; i++) {
          const int r = 4 * i + (lane >> 3), c = lane & 7;
          const uint4 v = *(const uint4*)(smem + OFF_T + warp * 2048 + r * 128 + ((c ^ (r & 7)) << 4));
          *(uint4*)(out + (size_t)(2 * rb + wg + 32 * (16 * w + r)) * 512 + 64 * (q4 + 4 * rank) + 8 * c) = v;
        }
      }
      if (tid == 0) { PROF_EV(15); PROF_CK(41); }
      if (tid == 128) PROF_EV(30);
    }
  } else if (warp < 12) {
    asm volatile("setmaxnreg.dec.sync.aligned.u32 104;");
    asm volatile("barrier.cluster.arrive.relaxed.aligned;" ::: "memory");
    const int t = tid - 256, w = warp - 8;
    const uint32_t ep = ld_x1(&ws->epoch[blockIdx.x * 8]);
    const uint32_t tag = (ep + 1) & 1;
    auto w_issue = [&](const CUtensorMap* m) {

      if (elect_one()) { mbar_expect_tx(bars + 8 * (B_WR + w), 3072); tma4d(sb + OFF_T + w * 3072, m, bars + 8 * (B_WR + w), 16 * kg, 0, 2 * w, tn); }

          __syncwarp();
    };
    auto gate_rows = [&] {
      const int r = 16 * j + 4 * w + (lane >> 3);
      const uint4* pg = (const uint4*)gate_w + (lane & 7);
      {
        float a = 0.f;
        asm volatile("bar.sync 4, 256;" ::: "memory");
#pragma unroll 1
        for (int hf = 0; hf < 2; hf++) {
          uint4 v[4], u[4];
#pragma unroll
          for (int kb = 0; kb < 4; kb++) v[kb] = __ldg(pg + (4 * hf + kb) * 8);
          mbar_wait(bars + 8 * (B_FE + 1 + 2 * hf), 0);
          if (hf) w_issue(&maps.wr);
#pragma unroll
          for (int kb = 0; kb < 4; kb++) u[kb] = *(const uint4*)(smem + (4 * hf + kb) * U + r * 128 + (((lane ^ r) & 7) << 4));
#pragma unroll
          for (int kb = 0; kb < 4; kb++) {
            const uint32_t uu[4] = {u[kb].x, u[kb].y, u[kb].z, u[kb].w}, vv[4] = {v[kb].x, v[kb].y, v[kb].z, v[kb].w};
#pragma unroll
            for (int e = 0; e < 4; e++) {
              uint32_t pr;
              asm("mul.rn.bf16x2 %0, %1, %2;" : "=r"(pr) : "r"(uu[e]), "r"(vv[e]));
              a += bf_lo(pr) + bf_hi(pr);
            }
          }
        }
#pragma unroll
        for (int o = 4; o; o >>= 1) a += __shfl_xor_sync(0xffffffffu, a, o);
        if ((lane & 7) == 0)
          asm volatile("st.relaxed.gpu.global.u32 [%0], %1;" ::"l"(ws->gate + rb * 128 + r),
                       "r"(pack_bf16(0.f, __fdividef(1.0f, 1.0f + __expf(-bf_lo(pack_bf16(a, 0.f))))) | tag) : "memory");
        if (t == 0) PROF_EV(18);
      }
    };
    {
      const int g = lane >> 2, q = lane & 3;
      uint32_t wf[32];
      if (!helper) {
        gate_rows();
        const uint32_t wa = sb + OFF_T + w * (3072 + 4) + q * 48 + g * 4;
#pragma unroll 1
        for (int ri = 0; ri < 2; ri++) {
          mbar_wait(bars + 8 * (B_WR + w), ri);
#pragma unroll
          for (int n2 = 0; n2 < 32 / WB; n2++) {
            uint32_t v[WB];
#pragma unroll
            for (int i = 0; i < WB; i++) {
              const int e = n2 * WB + i;
              asm volatile("ld.shared.u16 %0, [%1];" : "=r"(v[i]) : "r"(wa + ((e >> 1) & 7) * 192 + (e & 1) * (1536 + 2) + (e >> 4) * 2) : "memory");
            }
#pragma unroll
            for (int i = 0; i < WB; i++) wf[n2 * WB + i] = __byte_perm(wf[n2 * WB + i], v[i], 0x5432);
            if (WSLEEP) { asm volatile("nanosleep.u32 %0;" ::"r"(WSLEEP + (v[WB - 1] >> 16)) : "memory"); }
          }
          __syncwarp();
          if (ri == 0) w_issue(&maps.wi);
        }
        asm volatile("bar.sync 1, 128;" ::: "memory");
        if (t == 0) PROF_EV(11);
      } else {
        asm volatile("bar.sync 4, 256;" ::: "memory");
        hint_wait(&ws->cntW[0], (ep + 1) * 128u);
        const uint32_t t0 = (uint32_t)clock();
#pragma unroll 1
        for (;;) {
          uint32_t bad = 0;
#pragma unroll
          for (int i = 0; i < 32; i++) {
            const float2 v = ld_x2((const float2*)ws->Wh + (i >> 4) * 2048 + 16 * w + g + 8 * (i & 1) + 64 * q + ((i >> 1) & 7) * 256);
            wf[i] = __float_as_uint(v.x); bad |= __float_as_uint(v.y) ^ tag;
          }
          if (!__any_sync(0xffffffffu, bad & 1)) break;
          spin_guard(t0);
        }
        if (t == 0) PROF_EV(11);
      }
      if (w == 0 && elect_one()) { mbar_expect_tx(bars + 8 * B_W, 8192); bulk_load(sb + OFF_D, dtab, 8192, bars + 8 * B_W); }
      asm volatile("barrier.cluster.wait.aligned;" ::: "memory");
      mbar_wait(bars + 8 * B_W, 0);
      mbar_wait(bars + 8 * B_HX, 0);
      if (t == 0) PROF_EV(12);
      const uint32_t dd = (sb & 0x3FFFF) >> 4;
      const uint64_t dF = d128((dd + (OFF_D >> 4)) | (512u << 16)), dI = d128((dd + (OFF_D >> 4)) | (1u << 16)), dA = d128((dd + (OFF_XB >> 4)) | (512u << 16));
      float az[32];
      const int zero = blockIdx.x >> 16;
      uint32_t pf[32];
#pragma unroll
      for (int mt = 0; mt < 2; mt++) {
        wg_fence();
        if (mt == 0) mma_ss64<0, 3, 0>(az, dA, dF);
        else mma_ss64<0, 3, 2>(az, dA + 512, dF, zero);
#pragma unroll
        for (int k = 1; k < 4; k++) mma_ss64<0, 3, 1>(az, dA + (mt * 512 + k * 128), dF + k * 128);
        wg_commit();
        wg_wait<0>();
        fence_regs<0, 32>(az);
#pragma unroll
        for (int i = 0; i < 16; i++) {
          const float wr = bf_lo(wf[16 * mt + i]), wi = bf_hi(wf[16 * mt + i]);
          pf[16 * mt + i] = pack_pin(fmaf(az[2 * i], wr, -az[2 * i + 1] * wi), fmaf(az[2 * i], wi, az[2 * i + 1] * wr));
        }
      }
      if (t == 0) PROF_EV(16);
      {
        const int m = lane >> 3;
        const uint32_t a0 = sb + OFF_XB + w * 4096 + (m & 1) * 1024 + (m >> 1) * 128 + (lane & 7) * 16;
        uint32_t pk[16];
#pragma unroll
        for (int mt = 0; mt < 3; mt++) {
          if (mt < 2) {
            wg_fence();
            mma_rs64<0, 0, 2>(az, pf[16 * mt], pf[16 * mt + 1], pf[16 * mt + 2], pf[16 * mt + 3], dI, mt ? (int)helper : zero);
#pragma unroll
            for (int k = 1; k < 4; k++) mma_rs64<0, 0, 1>(az, pf[16 * mt + 4 * k], pf[16 * mt + 4 * k + 1], pf[16 * mt + 4 * k + 2], pf[16 * mt + 4 * k + 3], dI + k * 2);
            wg_commit();
          }
          if (mt > 0 && !helper) {
#pragma unroll
            for (int i = 0; i < 4; i++) stsm4t(a0 + (mt - 1) * 2048 + i * 256, pk[4 * i], pk[4 * i + 1], pk[4 * i + 2], pk[4 * i + 3]);
          }
          if (mt < 2) {
            wg_wait<0>();
            fence_regs<0, 32>(az);
#pragma unroll
            for (int i = 0; i < 16; i++) pk[i] = pack_pin(az[2 * i], az[2 * i + 1]);
          }
        }
      }
      if (helper) {
#pragma unroll
        for (int i = 0; i < 16; i++) {
          const int n = i >> 1, s0 = 4 * n + q;
          if ((n & 1) == (int)(blockIdx.x & 1)) st_u2(ws->Ts + s0 * 64 + 16 * w + g + 8 * (i & 1), pack_bf16(az[2 * i], az[2 * i + 1]), tag);
        }
        __syncwarp();
        hint_add_if(lane == 0, &ws->cntH[0]);
        if (t == 0) { ws->epoch[blockIdx.x * 8] = ep + 1; PROF_EV(13); }
      } else {
        asm volatile("fence.proxy.async.shared::cta;" ::: "memory");
        __syncwarp();
        if (elect_one()) {
          if (t == 0) PROF_EV(17);
          if (SPACE) __nanosleep(SPACE * w);
          asm volatile("cp.async.bulk.tensor.4d.global.shared::cta.bulk_group [%0, {%2, %3, %4, %5}], [%1];" ::"l"(&maps.ts), "r"(sb + OFF_XB + w * 4096),
                       "r"(16 * (kg & 3)), "r"(0), "r"(8 * tn + 2 * w), "r"(2 * q4) : "memory");
          bulk_done_signal(&ws->cntT[32 * q4]);
          asm volatile("mbarrier.arrive.shared::cluster.b64 _, [%0];" ::"r"(mapa(bars + 8 * B_RD0, rank ^ 1)) : "memory");
          if (t == 96) PROF_EV(13);
        }
        __syncwarp();
        if (j == 0) {
          hint_wait(&ws->cntH[0], (ep + 1) * 8u);
          const uint32_t t0 = (uint32_t)clock();
          float2 v;
          do { v = ld_x2((const float2*)ws->Ts + 2 * rb * 64 + t); spin_guard(t0); } while (__any_sync(0xffffffffu, (__float_as_uint(v.y) ^ tag) & 1));
          mbar_wait(bars + 8 * B_TL, 0);
          const uint32_t u = __float_as_uint(v.x);
          *(uint16_t*)(smem + OFF_T + t * 128 + ((t & 7) << 4)) = (uint16_t)u;
          *(uint16_t*)(smem + OFF_T + t * 128 + (((t & 7) ^ 1) << 4)) = (uint16_t)(u >> 16);
          asm volatile("fence.proxy.async.shared::cta;" ::: "memory");
          __syncwarp();
          mbar_arrive_if(lane == 0, bars + 8 * B_T);
        }
      }
    }
  } else {
    asm volatile("setmaxnreg.dec.sync.aligned.u32 24;");
    auto xf_load = [&](int q) {
      const uint32_t fb = bars + 8 * (B_FX + q);
      mbar_expect_tx(fb, U + 8192);
      tma3d(sb + q * U, &maps.x, fb, 64 * q, 0, 2 * rb);
      if (q >= 4) mbar_wait(bars + 8 * (B_FE + ((q - 4) >> 1)), 0);
      tma2d(sb + OFF_XB + (q & 3) * 8192, &maps.ft, fb, 64 * q, 64 * j);
    };
    if (elect_one()) {
      if (warp == 14) {
#pragma unroll
        for (int i = 0; i < B_FT; i++) mbar_init(bars + 8 * i, 1);
        asm volatile("fence.mbarrier_init.release.cluster;" ::: "memory");
        if (!helper) {
#pragma unroll 1
          for (int n = 0; n < 2; n++) {
            const uint32_t fb = bars + 8 * (B_FA + n);
            xf_load(2 * n); xf_load(2 * n + 1);
            mbar_expect_tx(fb, U);
            tma2d(sb + OFF_RING + n * U, &maps.g64, fb, f_full, 64 * n);
            tma2d(sb + OFF_RING + n * U + 8192, &maps.u64, fb, f_full, 64 * n);
          }
        }
      } else if (warp == 15) {
#pragma unroll
        for (int i = B_FT; i < NBAR; i++) mbar_init(bars + 8 * i, i < B_EA ? 1 : i < B_T ? 2 : 4);
#pragma unroll
        for (int i = 0; i < 8; i++) mbar_expect_tx(bars + 8 * (B_Z + i), U / 2);
        asm volatile("fence.mbarrier_init.release.cluster;" ::: "memory");
        asm volatile("fence.proxy.async.shared::cta;" ::: "memory");
      }
    }
    __syncwarp();
    asm volatile("bar.arrive 0, 384;" ::: "memory");
    asm volatile("bar.arrive 4, 256;" ::: "memory");
    __syncwarp();
    asm volatile("barrier.cluster.arrive.relaxed.aligned;" ::: "memory");
    asm volatile("bar.sync 3, 128;" ::: "memory");
    if (warp == 15 && !helper) {
        mbar_wait(bars + 8 * B_FE, 0);
        const uint32_t tag = (ld_x1(&ws->epoch[blockIdx.x * 8]) + 1) & 1;
        const int c = lane >> 4, jj = 16 * blockIdx.x + (lane & 15), jm = (2048 - jj) & 2047;
        const unsigned short* pr = (const unsigned short*)w_r + 256 * c;
        const unsigned short* pi = (const unsigned short*)w_i + 256 * c;
        const float wr = 0.25f * (bf_lo(__ldg(pr + jj * 257)) + bf_lo(__ldg(pr + jm * 257)));
        const float wi = 0.25f * (bf_lo(__ldg(pi + jj * 257)) - bf_lo(__ldg(pi + jm * 257)));
        st_u2(ws->Wh + c * 2048 + jj, c ? pack_bf16(-wi, wr) : pack_bf16(wr, wi), tag);
        __syncwarp();
        hint_add_if(lane == 0, &ws->cntW[0]);
        mbar_wait(bars + 8 * B_XS, 0);
        const uint32_t t0 = (uint32_t)clock();
        uint4 v;
        do { v = ld_x4(ws->gate + rb * 128 + 4 * lane); spin_guard(t0); } while (__any_sync(0xffffffffu, ((v.x ^ tag) | (v.y ^ tag) | (v.z ^ tag) | (v.w ^ tag)) & 1));
        *(uint4*)(smem + OFF_G + lane * 16) = v;
        __syncwarp();
        mbar_arrive_if(lane < 4, bars + 8 * B_G);
      }
    auto part_load = [&](int i, unsigned ep1) {
      const uint32_t bytes = i < 2 ? U : U / 2;
      mbar_wait(bars + 8 * (B_PZ + (i == 0)), 0);
      mbar_expect_tx(bars + 8 * (B_HP + i), bytes);
      flag_wait(&ws->cntP[32 * (rb * 8 + j) + 8 * i], ep1 * (i < 2 ? 8u : 4u));
      bulk_load(sb + (i == 0 ? OFF_T : i == 1 ? 0 : i * (U / 2)), ws->part + (size_t)(rb * 8 + j) * 3072 + (i < 2 ? i * 1024 : 1024 + i * 512), bytes, bars + 8 * (B_HP + i));
      if (i == 2) PROF_EV(26);
    };
    if ((!helper || warp == 15) && elect_one()) {
      if (warp < 14) {
        const int p = warp - 12;
#pragma unroll 1
        for (int i = 4 + p; i < 14; i += 2) asm volatile("prefetch.tensormap [%0];" ::"l"((const char*)&maps + i * 128) : "memory");
#pragma unroll 1
        for (int n = 2; n < 31; n++) {
          const bool table = n == 4 || n >= 29;
          const bool half = n >= 17 && n < 21;
          const int q = n < 4 ? n : n < 17 ? n - 1 : n - 5;
          const CUtensorMap* m = table ? &maps.e : half ? &maps.g32 + p : &maps.g64 + p;
          const int c0 = table ? 0 : half ? f_half : f_full + 64 * (q >> 3);
          const int c1 = table ? (2 * rb + ((n & 1) ^ 1)) * 128 + 64 * p : half ? 128 * (n - 17) : 64 * (q & 7);
          const uint32_t fb = bars + 8 * (B_FA + (n & 3)), dst = sb + OFF_RING + (n & 3) * U + p * 8192;
          if (n < 4) mbar_wait(bars + 8 * (B_FE + n - 2), 0);
          else mbar_wait(bars + 8 * (B_EA + (n & 3)), ((n >> 2) & 1) ^ 1);
          tma2d(dst, m, fb, c0, c1);
          if (p == 0) mbar_expect_tx(fb, U);
        }
        part_load(2 + p, ld_x1(&ws->epoch[blockIdx.x * 8]) + 1);
      } else if (warp == 15) {
        const unsigned ep1 = ld_x1(&ws->epoch[blockIdx.x * 8]) + 1;
        flag_wait(&ws->cntX[helper ? 0 : 32 * j], ep1 * 16u);
        PROF_EV(22);
        mbar_expect_tx(bars + 8 * B_HX, U);
        bulk_load(sb + OFF_XB, ws->X + (size_t)(helper ? 128 : kg * 8 + tn) * 8192, U, bars + 8 * B_HX);
        if (!helper) {
          flag_wait(&ws->cntT[32 * q4], ep1 * 128u);
          PROF_EV(23);
          mbar_expect_tx(bars + 8 * B_TL, U);
          tma3d(sb + OFF_T, &maps.t, bars + 8 * B_TL, 64 * j, 0, 2 * rb);
          part_load(0, ep1); part_load(1, ep1);
          mbar_wait(bars + 8 * (B_HP + 2), 0); mbar_wait(bars + 8 * (B_HP + 3), 0);
          ws->epoch[blockIdx.x * 8] = ep1;
        }
      } else {
#pragma unroll 1
        for (int q = 4; q < 8; q++) xf_load(q);
        mbar_wait(bars + 8 * (B_FE + 2), 0);
        mbar_expect_tx(bars + 8 * B_E0, U);
        tma2d(sb + OFF_XB, &maps.e, bars + 8 * B_E0, 0, 2 * rb * 128);
        tma2d(sb + OFF_XB + 8192, &maps.e, bars + 8 * B_E0, 0, 2 * rb * 128 + 64);
#pragma unroll 1
        for (int h2 = 0; h2 < 2; h2++) {
          const int sg = 2 * rb + h2;
          mbar_wait(bars + 8 * (B_XS + h2), 0);
#pragma unroll 1
          for (int c = 0; c < 2; c++) {
            asm volatile("cp.async.bulk.tensor.4d.global.shared::cta.bulk_group [%0, {%2, %3, %4, %5}], [%1];" ::"l"(&maps.xs),
                         "r"(sb + OFF_XB + h2 * 8192 + c * 4096), "r"(0), "r"(sg), "r"(0), "r"(16 * j + 8 * c) : "memory");
            if (j == 0)
              asm volatile("cp.async.bulk.global.shared::cta.bulk_group [%0], [%1], 256;" ::"l"(ws->X + 128 * 8192 + c * 4096 + sg * 128),
                           "r"(sb + OFF_SP + h2 * 512 + c * 256) : "memory");
            if (SPACE && h2 + c < 2) __nanosleep(SPACE);
          }
        }
        bulk_done_signal(&ws->cntX[32 * j]);
        PROF_EV(20);
#pragma unroll 1
        for (int t = 0; t < 8; t++) {
          const int col = 64 * (((q4 + 1 + (t >> 1)) & 3) + 4 * ((t & 1) ? rank : 1 - rank));
          const uint32_t fb = bars + 8 * (B_FT + (t & 3)), dst = sb + (t & 3) * TB;
          mbar_wait(bars + 8 * (B_ET + (t < 3 ? t + 1 : t & 3)), t >> 2);
          mbar_expect_tx(fb, (t & 1) ? TB : 28672);
          if (t & 1) tma3d(dst + 28672, &maps.fg, fb, col, 16 * rank, 4 * q4);
          tma2d(dst, &maps.d224, fb, col, 224 * j);
        }
      }
    }
  }
}

typedef CUresult (*EncodeFn)(CUtensorMap*, CUtensorMapDataType, cuuint32_t, void*, const cuuint64_t*, const cuuint64_t*, const cuuint32_t*,
                             const cuuint32_t*, CUtensorMapInterleave, CUtensorMapSwizzle, CUtensorMapL2promotion, CUtensorMapFloatOOBfill);

static void encode(EncodeFn f, CUtensorMap* m, const void* base, int rank, const cuuint64_t* dims, const cuuint64_t* strides, const cuuint32_t* box,
                   CUtensorMapSwizzle sw) {
  cuuint32_t es[5] = {1, 1, 1, 1, 1};
  f(m, CU_TENSOR_MAP_DATA_TYPE_BFLOAT16, rank, (void*)base, dims, strides, box, es, CU_TENSOR_MAP_INTERLEAVE_NONE, sw,
    CU_TENSOR_MAP_L2_PROMOTION_L2_128B, CU_TENSOR_MAP_FLOAT_OOB_FILL_NONE);
}

extern "C" void kernel_launch(void* const* d_in, const int* in_sizes, int n_in, void* d_out, int out_size) {
  (void)in_sizes; (void)n_in; (void)out_size;
  const __nv_bfloat16* x = (const __nv_bfloat16*)d_in[0];
  const __nv_bfloat16* w_r = (const __nv_bfloat16*)d_in[1];
  const __nv_bfloat16* w_i = (const __nv_bfloat16*)d_in[2];
  const __nv_bfloat16* Wg = (const __nv_bfloat16*)d_in[4];
  const __nv_bfloat16* Wu = (const __nv_bfloat16*)d_in[5];
  const __nv_bfloat16* Wd = (const __nv_bfloat16*)d_in[6];
  const __nv_bfloat16* gw = (const __nv_bfloat16*)d_in[7];

  void* fp = nullptr; cudaDriverEntryPointQueryResult qr;
  cudaGetDriverEntryPoint("cuTensorMapEncodeTiled", &fp, cudaEnableDefault, &qr);
  EncodeFn enc = (EncodeFn)fp;
  void *pFT, *pET, *pDT, *pW;
  cudaGetSymbolAddress(&pDT, g_DT); cudaGetSymbolAddress(&pW, g_work);
  void *pX = ((Work*)pW)->X, *pT = ((Work*)pW)->T;
  cudaGetSymbolAddress(&pFT, g_FT); cudaGetSymbolAddress(&pET, g_ET);

  Maps mp;
  const CUtensorMapSwizzle S128 = CU_TENSOR_MAP_SWIZZLE_128B, S64 = CU_TENSOR_MAP_SWIZZLE_64B;
  { cuuint64_t d[3] = {512, 64, 32}, s[2] = {32768, 1024}; cuuint32_t b[3] = {64, 64, 2}; encode(enc, &mp.x, x, 3, d, s, b, S128); }
  { cuuint64_t d[2] = {512, 512}, s[1] = {1024}; cuuint32_t b[2] = {64, 64}; encode(enc, &mp.ft, pFT, 2, d, s, b, S128); }
  { cuuint64_t d[4] = {128, 32, 2, 129}, s[3] = {256, 8192, 16384}; cuuint32_t b[4] = {128, 1, 2, 8}; encode(enc, &mp.xs, pX, 4, d, s, b, CU_TENSOR_MAP_SWIZZLE_NONE); }
  { cuuint64_t d[4] = {64, 32, 64, 8}, s[3] = {65536, 1024, 128}; cuuint32_t b[4] = {16, 32, 2, 2}; encode(enc, &mp.ts, pT, 4, d, s, b, CU_TENSOR_MAP_SWIZZLE_NONE); }
  { cuuint64_t d[3] = {512, 32, 16}, s[2] = {1024, 32768}; cuuint32_t b[3] = {64, 16, 4}; encode(enc, &mp.fg, pFT, 3, d, s, b, S128); }
  { cuuint64_t d[3] = {512, 64, 32}, s[2] = {1024, 65536}; cuuint32_t b[3] = {64, 64, 2}; encode(enc, &mp.t, pT, 3, d, s, b, S128); }
  { cuuint64_t d[2] = {64, 4096}, s[1] = {128}; cuuint32_t b[2] = {64, 64}; encode(enc, &mp.e, pET, 2, d, s, b, S128); }
  { cuuint64_t d[2] = {1792, 512}, s[1] = {3584}; cuuint32_t b[2] = {64, 64}, b2[2] = {32, 128};
    encode(enc, &mp.g64, Wg, 2, d, s, b, S128); encode(enc, &mp.u64, Wu, 2, d, s, b, S128);
    encode(enc, &mp.g32, Wg, 2, d, s, b2, S64); encode(enc, &mp.u32, Wu, 2, d, s, b2, S64); }
  { cuuint64_t d[2] = {512, 1792}, s[1] = {1024}; cuuint32_t b[2] = {64, 224}; encode(enc, &mp.d224, Wd, 2, d, s, b, S128); }
  { cuuint64_t d[4] = {264, 32, 8, 8}, s[3] = {32896, 512, 4112}; cuuint32_t b[4] = {24, 32, 2, 1};
    encode(enc, &mp.wr, w_r, 4, d, s, b, CU_TENSOR_MAP_SWIZZLE_NONE); encode(enc, &mp.wi, w_i, 4, d, s, b, CU_TENSOR_MAP_SWIZZLE_NONE); }

  cudaFuncSetAttribute(fused_kernel, cudaFuncAttributeMaxDynamicSharedMemorySize, SMEM_BYTES);
  fused_kernel<<<NCTA, 512, SMEM_BYTES>>>((Work*)pW, (const uint16_t*)pDT, w_r, w_i, gw, x, (__nv_bfloat16*)d_out, mp);
}
```

```cpp
#include <cuda_runtime.h>
#include <cuda_bf16.h>
#include <cuda.h>
#include <stdint.h>

namespace tbl {
constexpr double PI = 3.14159265358979323846264338327950288;
constexpr double sin_s(double x) { double t = x, s = x; for (int n = 1; n < 12; n++) { t *= -x * x / ((2 * n) * (2 * n + 1)); s += t; } return s; }
constexpr double cos_s(double x) { double t = 1, s = 1; for (int n = 1; n < 12; n++) { t *= -x * x / ((2 * n - 1) * (2 * n)); s += t; } return s; }
constexpr double cos2048(int m) {
  m &= 2047; if (m > 1024) m = 2048 - m;
  bool neg = false; if (m > 512) { m = 1024 - m; neg = true; }
  double v = (m <= 256) ? cos_s(2 * PI * m / 2048) : sin_s(2 * PI * (512 - m) / 2048);
  return neg ? -v : v;
}
constexpr uint16_t to_bf16(double v) {
  if (v == 0) return 0;
  uint16_t s = 0; if (v < 0) { s = 0x8000; v = -v; }
  int e = 0; while (v >= 2) { v /= 2; e++; } while (v < 1) { v *= 2; e--; }
  double m = (v - 1) * 128; int mi = (int)m; double fr = m - mi;
  if (fr > 0.5 || (fr == 0.5 && (mi & 1))) mi++;
  if (mi == 128) { mi = 0; e++; }
  return (uint16_t)(s | ((e + 127) << 7) | mi);
}
struct CosT { uint16_t v[2048]; constexpr CosT() : v() { for (int i = 0; i < 2048; i++) v[i] = to_bf16(cos2048(i)); } };
struct alignas(1024) FT {
  uint16_t v[512 * 512];
  constexpr FT() : v() {
    CosT c;
    for (int r = 0; r < 512; r++) {
      int k = (r >> 5) * 16 + 2 * (r & 7) + ((r >> 4) & 1), e = (r >> 3) & 1;
      int mul = 4 * k, add = e ? 512 : 0;
      if (k == 0 && e == 1) { mul = 1024; add = 0; }
      for (int d = 0; d < 512; d++) v[r * 512 + d] = c.v[(d * mul + add) & 2047];
    }
  }
};
struct alignas(1024) ET {
  uint16_t v[2048 * 128];
  constexpr ET() : v() {
    CosT c;
    for (int s = 0; s < 2048; s++)
      for (int j = 0; j < 64; j++) {
        const int o = (s & 31) * 8192 + (s >> 5) * 64 + j;
        v[o] = c.v[(s * j) & 2047]; v[o + 4096] = c.v[(s * j + 512) & 2047];
      }
  }
};
struct alignas(1024) DT {
  uint16_t v[64 * 64];
  constexpr DT() : v() {
    CosT c;
    for (int r = 0; r < 64; r++)
      for (int n = 0; n < 64; n++) {
        const int s0 = r >> 1, e = r & 1, f = n & 1;
        const int m = 64 * s0 * (n >> 1) + (e == f ? 0 : e ? -512 : 512);
        v[r * 64 + (((n >> 3) ^ (r & 7)) << 3) + (n & 7)] = c.v[m & 2047];
      }
  }
};
}

__device__ constexpr tbl::FT g_FT = tbl::FT();
__device__ constexpr tbl::ET g_ET = tbl::ET();
__device__ constexpr tbl::DT g_DT = tbl::DT();

struct alignas(1024) Work {
  unsigned epoch[132 * 8];
  unsigned cntX[8 * 32], cntT[8 * 32], cntP[128 * 32], cntW[32], cntH[32];
  alignas(16) float gate[16 * 128];
  alignas(16) uint2 Wh[2 * 2048];
  alignas(16) uint2 Ts[32 * 64];
  alignas(1024) uint16_t X[129 * 8192];
  alignas(1024) uint16_t T[32 * 64 * 512];
  alignas(1024) uint4 part[128 * 3 * 1024];
};
__device__ Work g_work;
#define PROF_EV(i) do {} while (0)
#define PROF_CK(i) do {} while (0)

__device__ __forceinline__ uint32_t smem_u32(const void* p) { return (uint32_t)__cvta_generic_to_shared(p); }
__device__ __forceinline__ void mbar_init(uint32_t bar, uint32_t cnt) { asm volatile("mbarrier.init.shared::cta.b64 [%0], %1;" ::"r"(bar), "r"(cnt)); }
__device__ __forceinline__ void mbar_expect_tx(uint32_t bar, uint32_t bytes) { asm volatile("mbarrier.arrive.expect_tx.shared::cta.b64 _, [%0], %1;" ::"r"(bar), "r"(bytes) : "memory"); }
__device__ __forceinline__ void mbar_arrive(uint32_t bar) { asm volatile("mbarrier.arrive.shared::cta.b64 _, [%0];" ::"r"(bar) : "memory"); }
__device__ __forceinline__ bool elect_one() {
  uint32_t p;
  asm volatile("{\n.reg .pred p;\nelect.sync _|p, 0xffffffff;\nselp.u32 %0, 1, 0, p;\n}" : "=r"(p));
  return p;
}
__device__ __forceinline__ void mbar_arrive_if(bool p, uint32_t bar) {
  asm volatile("{\n.reg .pred p;\nsetp.ne.b32 p, %1, 0;\n@p mbarrier.arrive.shared::cta.b64 _, [%0];\n}" ::"r"(bar), "r"((int)p) : "memory");
}
__device__ __forceinline__ void hint_add_if(bool p, unsigned* a) {
  asm volatile("{\n.reg .pred p;\nsetp.ne.b32 p, %1, 0;\n@p red.relaxed.gpu.global.add.u32 [%0], 1;\n}" ::"l"(a), "r"((int)p) : "memory");
}
__device__ __forceinline__ bool mbar_try(uint32_t bar, uint32_t parity) {
  uint32_t ok;
  asm volatile("{\n.reg .pred p;\nmbarrier.test_wait.parity.shared::cta.b64 p, [%1], %2;\nselp.u32 %0, 1, 0, p;\n}" : "=r"(ok) : "r"(bar), "r"(parity) : "memory");
  return ok;
}
__device__ __forceinline__ void mbar_wait(uint32_t bar, uint32_t parity) {
  asm volatile(
      "{\n.reg .pred p;\n.reg .u32 n;\nmov.u32 n, 0;\n"
      "W_LOOP:\nmbarrier.try_wait.parity.shared::cta.b64 p, [%0], %1;\n@p bra W_DONE;\n"
      "add.u32 n, n, 1;\nsetp.lt.u32 p, n, 0x40000;\n@p bra W_LOOP;\ntrap;\nW_DONE:\n}" ::"r"(bar), "r"(parity) : "memory");
}
__device__ __forceinline__ void bulk_load(uint32_t dst, const void* src, uint32_t bytes, uint32_t bar) {
  asm volatile("cp.async.bulk.shared::cluster.global.mbarrier::complete_tx::bytes [%0], [%1], %2, [%3];" ::"r"(dst), "l"(src), "r"(bytes), "r"(bar) : "memory");
}
__device__ __forceinline__ void spin_guard(uint32_t t0) { if ((uint32_t)clock() - t0 > (1u << 30)) __trap(); }
__device__ __forceinline__ float2 ld_x2(const float2* p) { float2 v; asm volatile("ld.relaxed.gpu.global.v2.f32 {%0,%1}, [%2];" : "=f"(v.x), "=f"(v.y) : "l"(p) : "memory"); return v; }
__device__ __forceinline__ void st_u2(uint2* p, uint32_t a, uint32_t b) { asm volatile("st.relaxed.gpu.global.v2.u32 [%0], {%1,%2};" ::"l"(p), "r"(a), "r"(b) : "memory"); }
__device__ __forceinline__ uint32_t ld_x1(const void* p) { uint32_t v; asm volatile("ld.relaxed.gpu.global.u32 %0, [%1];" : "=r"(v) : "l"(p) : "memory"); return v; }
__device__ __forceinline__ uint4 ld_x4(const void* p) { uint4 v; asm volatile("ld.relaxed.gpu.global.v4.u32 {%0,%1,%2,%3}, [%4];" : "=r"(v.x), "=r"(v.y), "=r"(v.z), "=r"(v.w) : "l"(p) : "memory"); return v; }
__device__ __forceinline__ uint32_t mapa(uint32_t a, uint32_t cta) { uint32_t r; asm volatile("mapa.shared::cluster.u32 %0, %1, %2;" : "=r"(r) : "r"(a), "r"(cta)); return r; }
__device__ __forceinline__ void stsm4t(uint32_t a, uint32_t r0, uint32_t r1, uint32_t r2, uint32_t r3) {
  asm volatile("stmatrix.sync.aligned.m8n8.x4.trans.shared.b16 [%0], {%1,%2,%3,%4};" ::"r"(a), "r"(r0), "r"(r1), "r"(r2), "r"(r3) : "memory");
}
__device__ __forceinline__ void hint_add(unsigned* p) { asm volatile("red.relaxed.gpu.global.add.u32 [%0], 1;" ::"l"(p) : "memory"); }
__device__ __forceinline__ void hint_wait(const unsigned* p, unsigned target) {
  const uint32_t t0 = (uint32_t)clock();
  while ((int)(ld_x1(p) - target) < 0) spin_guard(t0);
}
__device__ __forceinline__ void bulk_done_signal(unsigned* p) {
  asm volatile("cp.async.bulk.commit_group;\ncp.async.bulk.wait_group 0;\nfence.proxy.async.global;" ::: "memory");
  hint_add(p);
}
__device__ __forceinline__ void flag_wait(const unsigned* p, unsigned target) {
  hint_wait(p, target);
  asm volatile("fence.proxy.async.global;" ::: "memory");
}
__device__ __forceinline__ void tma2d(uint32_t dst, const CUtensorMap* m, uint32_t bar, int c0, int c1) {
  asm volatile("cp.async.bulk.tensor.2d.shared::cluster.global.mbarrier::complete_tx::bytes [%0], [%1, {%3, %4}], [%2];" ::"r"(dst), "l"(m), "r"(bar), "r"(c0), "r"(c1) : "memory");
}
__device__ __forceinline__ void tma3d(uint32_t dst, const CUtensorMap* m, uint32_t bar, int c0, int c1, int c2) {
  asm volatile("cp.async.bulk.tensor.3d.shared::cluster.global.mbarrier::complete_tx::bytes [%0], [%1, {%3, %4, %5}], [%2];" ::"r"(dst), "l"(m), "r"(bar), "r"(c0), "r"(c1), "r"(c2) : "memory");
}
__device__ __forceinline__ void tma4d(uint32_t dst, const CUtensorMap* m, uint32_t bar, int c0, int c1, int c2, int c3) {
  asm volatile("cp.async.bulk.tensor.4d.shared::cluster.global.mbarrier::complete_tx::bytes [%0], [%1, {%3, %4, %5, %6}], [%2];" ::"r"(dst), "l"(m), "r"(bar), "r"(c0), "r"(c1), "r"(c2), "r"(c3) : "memory");
}
__device__ __forceinline__ void wg_fence() { asm volatile("wgmma.fence.sync.aligned;" ::: "memory"); }
__device__ __forceinline__ void wg_commit() { asm volatile("wgmma.commit_group.sync.aligned;" ::: "memory"); }
template <int N> __device__ __forceinline__ void wg_wait() { asm volatile("wgmma.wait_group.sync.aligned %0;" ::"n"(N) : "memory"); }
template <int O, int N, int NN> __device__ __forceinline__ void fence_regs(float (&d)[NN]) {
#pragma unroll
  for (int i = 0; i < N; i++) asm volatile("" : "+f"(d[O + i])::"memory");
}
__device__ __forceinline__ uint32_t pack_bf16(float lo, float hi) {
  uint32_t r; asm("cvt.rn.bf16x2.f32 %0, %1, %2;" : "=r"(r) : "f"(hi), "f"(lo)); return r;
}
__device__ __forceinline__ uint32_t pack_pin(float lo, float hi) {
  uint32_t r; asm volatile("cvt.rn.bf16x2.f32 %0, %1, %2;" : "=r"(r) : "f"(hi), "f"(lo) : "memory"); return r;
}
__device__ __forceinline__ uint32_t add_bf2(uint32_t a, uint32_t b) { uint32_t r; asm("add.rn.bf16x2 %0, %1, %2;" : "=r"(r) : "r"(a), "r"(b)); return r; }
__device__ __forceinline__ float bf_lo(uint32_t u) { return __uint_as_float(u << 16); }
__device__ __forceinline__ float bf_hi(uint32_t u) { return __uint_as_float(u & 0xffff0000u); }

__device__ __forceinline__ uint64_t d128(uint32_t lo) { uint64_t d; asm("mov.b64 %0, {%1, 0x40000040};" : "=l"(d) : "r"(lo)); return d; }
__device__ __forceinline__ uint64_t d64(uint32_t lo) { uint64_t d; asm("mov.b64 %0, {%1, 0x80000020};" : "=l"(d) : "r"(lo)); return d; }
template<int O,int TB,int ACC,int NN> __device__ __forceinline__ void mma_ss64(float (&d)[NN], uint64_t da, uint64_t db, int sd = 0){
  if constexpr (ACC == 1) asm volatile("wgmma.mma_async.sync.aligned.m64n64k16.f32.bf16.bf16 {%0,%1,%2,%3,%4,%5,%6,%7,%8,%9,%10,%11,%12,%13,%14,%15,%16,%17,%18,%19,%20,%21,%22,%23,%24,%25,%26,%27,%28,%29,%30,%31}, %32, %33, 1, 1, 1, %35, %34;"
   : "+f"(d[O+0]), "+f"(d[O+1]), "+f"(d[O+2]), "+f"(d[O+3]), "+f"(d[O+4]), "+f"(d[O+5]), "+f"(d[O+6]), "+f"(d[O+7]), "+f"(d[O+8]), "+f"(d[O+9]), "+f"(d[O+10]), "+f"(d[O+11]), "+f"(d[O+12]), "+f"(d[O+13]), "+f"(d[O+14]), "+f"(d[O+15]), "+f"(d[O+16]), "+f"(d[O+17]), "+f"(d[O+18]), "+f"(d[O+19]), "+f"(d[O+20]), "+f"(d[O+21]), "+f"(d[O+22]), "+f"(d[O+23]), "+f"(d[O+24]), "+f"(d[O+25]), "+f"(d[O+26]), "+f"(d[O+27]), "+f"(d[O+28]), "+f"(d[O+29]), "+f"(d[O+30]), "+f"(d[O+31])
   : "l"(da), "l"(db), "n"(TB & 1), "n"(TB >> 1));
  else if constexpr (ACC == 0) asm volatile("wgmma.mma_async.sync.aligned.m64n64k16.f32.bf16.bf16 {%0,%1,%2,%3,%4,%5,%6,%7,%8,%9,%10,%11,%12,%13,%14,%15,%16,%17,%18,%19,%20,%21,%22,%23,%24,%25,%26,%27,%28,%29,%30,%31}, %32, %33, 0, 1, 1, %35, %34;"
   : "=f"(d[O+0]), "=f"(d[O+1]), "=f"(d[O+2]), "=f"(d[O+3]), "=f"(d[O+4]), "=f"(d[O+5]), "=f"(d[O+6]), "=f"(d[O+7]), "=f"(d[O+8]), "=f"(d[O+9]), "=f"(d[O+10]), "=f"(d[O+11]), "=f"(d[O+12]), "=f"(d[O+13]), "=f"(d[O+14]), "=f"(d[O+15]), "=f"(d[O+16]), "=f"(d[O+17]), "=f"(d[O+18]), "=f"(d[O+19]), "=f"(d[O+20]), "=f"(d[O+21]), "=f"(d[O+22]), "=f"(d[O+23]), "=f"(d[O+24]), "=f"(d[O+25]), "=f"(d[O+26]), "=f"(d[O+27]), "=f"(d[O+28]), "=f"(d[O+29]), "=f"(d[O+30]), "=f"(d[O+31])
   : "l"(da), "l"(db), "n"(TB & 1), "n"(TB >> 1));
  else asm volatile("{\n.reg .pred p;\nsetp.ne.b32 p, %36, 0;\nwgmma.mma_async.sync.aligned.m64n64k16.f32.bf16.bf16 {%0,%1,%2,%3,%4,%5,%6,%7,%8,%9,%10,%11,%12,%13,%14,%15,%16,%17,%18,%19,%20,%21,%22,%23,%24,%25,%26,%27,%28,%29,%30,%31}, %32, %33, p, 1, 1, %35, %34;\n}"
   : "+f"(d[O+0]), "+f"(d[O+1]), "+f"(d[O+2]), "+f"(d[O+3]), "+f"(d[O+4]), "+f"(d[O+5]), "+f"(d[O+6]), "+f"(d[O+7]), "+f"(d[O+8]), "+f"(d[O+9]), "+f"(d[O+10]), "+f"(d[O+11]), "+f"(d[O+12]), "+f"(d[O+13]), "+f"(d[O+14]), "+f"(d[O+15]), "+f"(d[O+16]), "+f"(d[O+17]), "+f"(d[O+18]), "+f"(d[O+19]), "+f"(d[O+20]), "+f"(d[O+21]), "+f"(d[O+22]), "+f"(d[O+23]), "+f"(d[O+24]), "+f"(d[O+25]), "+f"(d[O+26]), "+f"(d[O+27]), "+f"(d[O+28]), "+f"(d[O+29]), "+f"(d[O+30]), "+f"(d[O+31])
   : "l"(da), "l"(db), "n"(TB & 1), "n"(TB >> 1), "r"(sd));
}
template<int O,int TB,int ACC,int NN> __device__ __forceinline__ void mma_rs64(float (&d)[NN], uint32_t a0, uint32_t a1, uint32_t a2, uint32_t a3, uint64_t db, int sd = 0){
  if constexpr (ACC == 1) asm volatile("wgmma.mma_async.sync.aligned.m64n64k16.f32.bf16.bf16 {%0,%1,%2,%3,%4,%5,%6,%7,%8,%9,%10,%11,%12,%13,%14,%15,%16,%17,%18,%19,%20,%21,%22,%23,%24,%25,%26,%27,%28,%29,%30,%31}, {%32,%33,%34,%35}, %36, 1, 1, 1, %37;"
   : "+f"(d[O+0]), "+f"(d[O+1]), "+f"(d[O+2]), "+f"(d[O+3]), "+f"(d[O+4]), "+f"(d[O+5]), "+f"(d[O+6]), "+f"(d[O+7]), "+f"(d[O+8]), "+f"(d[O+9]), "+f"(d[O+10]), "+f"(d[O+11]), "+f"(d[O+12]), "+f"(d[O+13]), "+f"(d[O+14]), "+f"(d[O+15]), "+f"(d[O+16]), "+f"(d[O+17]), "+f"(d[O+18]), "+f"(d[O+19]), "+f"(d[O+20]), "+f"(d[O+21]), "+f"(d[O+22]), "+f"(d[O+23]), "+f"(d[O+24]), "+f"(d[O+25]), "+f"(d[O+26]), "+f"(d[O+27]), "+f"(d[O+28]), "+f"(d[O+29]), "+f"(d[O+30]), "+f"(d[O+31])
   : "r"(a0), "r"(a1), "r"(a2), "r"(a3), "l"(db), "n"(TB));
  else if constexpr (ACC == 0) asm volatile("wgmma.mma_async.sync.aligned.m64n64k16.f32.bf16.bf16 {%0,%1,%2,%3,%4,%5,%6,%7,%8,%9,%10,%11,%12,%13,%14,%15,%16,%17,%18,%19,%20,%21,%22,%23,%24,%25,%26,%27,%28,%29,%30,%31}, {%32,%33,%34,%35}, %36, 0, 1, 1, %37;"
   : "=f"(d[O+0]), "=f"(d[O+1]), "=f"(d[O+2]), "=f"(d[O+3]), "=f"(d[O+4]), "=f"(d[O+5]), "=f"(d[O+6]), "=f"(d[O+7]), "=f"(d[O+8]), "=f"(d[O+9]), "=f"(d[O+10]), "=f"(d[O+11]), "=f"(d[O+12]), "=f"(d[O+13]), "=f"(d[O+14]), "=f"(d[O+15]), "=f"(d[O+16]), "=f"(d[O+17]), "=f"(d[O+18]), "=f"(d[O+19]), "=f"(d[O+20]), "=f"(d[O+21]), "=f"(d[O+22]), "=f"(d[O+23]), "=f"(d[O+24]), "=f"(d[O+25]), "=f"(d[O+26]), "=f"(d[O+27]), "=f"(d[O+28]), "=f"(d[O+29]), "=f"(d[O+30]), "=f"(d[O+31])
   : "r"(a0), "r"(a1), "r"(a2), "r"(a3), "l"(db), "n"(TB));
  else asm volatile("{\n.reg .pred p;\nsetp.ne.b32 p, %38, 0;\nwgmma.mma_async.sync.aligned.m64n64k16.f32.bf16.bf16 {%0,%1,%2,%3,%4,%5,%6,%7,%8,%9,%10,%11,%12,%13,%14,%15,%16,%17,%18,%19,%20,%21,%22,%23,%24,%25,%26,%27,%28,%29,%30,%31}, {%32,%33,%34,%35}, %36, p, 1, 1, %37;\n}"
   : "+f"(d[O+0]), "+f"(d[O+1]), "+f"(d[O+2]), "+f"(d[O+3]), "+f"(d[O+4]), "+f"(d[O+5]), "+f"(d[O+6]), "+f"(d[O+7]), "+f"(d[O+8]), "+f"(d[O+9]), "+f"(d[O+10]), "+f"(d[O+11]), "+f"(d[O+12]), "+f"(d[O+13]), "+f"(d[O+14]), "+f"(d[O+15]), "+f"(d[O+16]), "+f"(d[O+17]), "+f"(d[O+18]), "+f"(d[O+19]), "+f"(d[O+20]), "+f"(d[O+21]), "+f"(d[O+22]), "+f"(d[O+23]), "+f"(d[O+24]), "+f"(d[O+25]), "+f"(d[O+26]), "+f"(d[O+27]), "+f"(d[O+28]), "+f"(d[O+29]), "+f"(d[O+30]), "+f"(d[O+31])
   : "r"(a0), "r"(a1), "r"(a2), "r"(a3), "l"(db), "n"(TB), "r"(sd));
}
template<int O,int TB,int ACC,int NN> __device__ __forceinline__ void mma_ss128(float (&d)[NN], uint64_t da, uint64_t db, int sd = 0){
  if constexpr (ACC == 1) asm volatile("wgmma.mma_async.sync.aligned.m64n128k16.f32.bf16.bf16 {%0,%1,%2,%3,%4,%5,%6,%7,%8,%9,%10,%11,%12,%13,%14,%15,%16,%17,%18,%19,%20,%21,%22,%23,%24,%25,%26,%27,%28,%29,%30,%31,%32,%33,%34,%35,%36,%37,%38,%39,%40,%41,%42,%43,%44,%45,%46,%47,%48,%49,%50,%51,%52,%53,%54,%55,%56,%57,%58,%59,%60,%61,%62,%63}, %64, %65, 1, 1, 1, %67, %66;"
   : "+f"(d[O+0]), "+f"(d[O+1]), "+f"(d[O+2]), "+f"(d[O+3]), "+f"(d[O+4]), "+f"(d[O+5]), "+f"(d[O+6]), "+f"(d[O+7]), "+f"(d[O+8]), "+f"(d[O+9]), "+f"(d[O+10]), "+f"(d[O+11]), "+f"(d[O+12]), "+f"(d[O+13]), "+f"(d[O+14]), "+f"(d[O+15]), "+f"(d[O+16]), "+f"(d[O+17]), "+f"(d[O+18]), "+f"(d[O+19]), "+f"(d[O+20]), "+f"(d[O+21]), "+f"(d[O+22]), "+f"(d[O+23]), "+f"(d[O+24]), "+f"(d[O+25]), "+f"(d[O+26]), "+f"(d[O+27]), "+f"(d[O+28]), "+f"(d[O+29]), "+f"(d[O+30]), "+f"(d[O+31]), "+f"(d[O+32]), "+f"(d[O+33]), "+f"(d[O+34]), "+f"(d[O+35]), "+f"(d[O+36]), "+f"(d[O+37]), "+f"(d[O+38]), "+f"(d[O+39]), "+f"(d[O+40]), "+f"(d[O+41]), "+f"(d[O+42]), "+f"(d[O+43]), "+f"(d[O+44]), "+f"(d[O+45]), "+f"(d[O+46]), "+f"(d[O+47]), "+f"(d[O+48]), "+f"(d[O+49]), "+f"(d[O+50]), "+f"(d[O+51]), "+f"(d[O+52]), "+f"(d[O+53]), "+f"(d[O+54]), "+f"(d[O+55]), "+f"(d[O+56]), "+f"(d[O+57]), "+f"(d[O+58]), "+f"(d[O+59]), "+f"(d[O+60]), "+f"(d[O+61]), "+f"(d[O+62]), "+f"(d[O+63])
   : "l"(da), "l"(db), "n"(TB & 1), "n"(TB >> 1));
  else if constexpr (ACC == 0) asm volatile("wgmma.mma_async.sync.aligned.m64n128k16.f32.bf16.bf16 {%0,%1,%2,%3,%4,%5,%6,%7,%8,%9,%10,%11,%12,%13,%14,%15,%16,%17,%18,%19,%20,%21,%22,%23,%24,%25,%26,%27,%28,%29,%30,%31,%32,%33,%34,%35,%36,%37,%38,%39,%40,%41,%42,%43,%44,%45,%46,%47,%48,%49,%50,%51,%52,%53,%54,%55,%56,%57,%58,%59,%60,%61,%62,%63}, %64, %65, 0, 1, 1, %67, %66;"
   : "=f"(d[O+0]), "=f"(d[O+1]), "=f"(d[O+2]), "=f"(d[O+3]), "=f"(d[O+4]), "=f"(d[O+5]), "=f"(d[O+6]), "=f"(d[O+7]), "=f"(d[O+8]), "=f"(d[O+9]), "=f"(d[O+10]), "=f"(d[O+11]), "=f"(d[O+12]), "=f"(d[O+13]), "=f"(d[O+14]), "=f"(d[O+15]), "=f"(d[O+16]), "=f"(d[O+17]), "=f"(d[O+18]), "=f"(d[O+19]), "=f"(d[O+20]), "=f"(d[O+21]), "=f"(d[O+22]), "=f"(d[O+23]), "=f"(d[O+24]), "=f"(d[O+25]), "=f"(d[O+26]), "=f"(d[O+27]), "=f"(d[O+28]), "=f"(d[O+29]), "=f"(d[O+30]), "=f"(d[O+31]), "=f"(d[O+32]), "=f"(d[O+33]), "=f"(d[O+34]), "=f"(d[O+35]), "=f"(d[O+36]), "=f"(d[O+37]), "=f"(d[O+38]), "=f"(d[O+39]), "=f"(d[O+40]), "=f"(d[O+41]), "=f"(d[O+42]), "=f"(d[O+43]), "=f"(d[O+44]), "=f"(d[O+45]), "=f"(d[O+46]), "=f"(d[O+47]), "=f"(d[O+48]), "=f"(d[O+49]), "=f"(d[O+50]), "=f"(d[O+51]), "=f"(d[O+52]), "=f"(d[O+53]), "=f"(d[O+54]), "=f"(d[O+55]), "=f"(d[O+56]), "=f"(d[O+57]), "=f"(d[O+58]), "=f"(d[O+59]), "=f"(d[O+60]), "=f"(d[O+61]), "=f"(d[O+62]), "=f"(d[O+63])
   : "l"(da), "l"(db), "n"(TB & 1), "n"(TB >> 1));
  else asm volatile("{\n.reg .pred p;\nsetp.ne.b32 p, %68, 0;\nwgmma.mma_async.sync.aligned.m64n128k16.f32.bf16.bf16 {%0,%1,%2,%3,%4,%5,%6,%7,%8,%9,%10,%11,%12,%13,%14,%15,%16,%17,%18,%19,%20,%21,%22,%23,%24,%25,%26,%27,%28,%29,%30,%31,%32,%33,%34,%35,%36,%37,%38,%39,%40,%41,%42,%43,%44,%45,%46,%47,%48,%49,%50,%51,%52,%53,%54,%55,%56,%57,%58,%59,%60,%61,%62,%63}, %64, %65, p, 1, 1, %67, %66;\n}"
   : "+f"(d[O+0]), "+f"(d[O+1]), "+f"(d[O+2]), "+f"(d[O+3]), "+f"(d[O+4]), "+f"(d[O+5]), "+f"(d[O+6]), "+f"(d[O+7]), "+f"(d[O+8]), "+f"(d[O+9]), "+f"(d[O+10]), "+f"(d[O+11]), "+f"(d[O+12]), "+f"(d[O+13]), "+f"(d[O+14]), "+f"(d[O+15]), "+f"(d[O+16]), "+f"(d[O+17]), "+f"(d[O+18]), "+f"(d[O+19]), "+f"(d[O+20]), "+f"(d[O+21]), "+f"(d[O+22]), "+f"(d[O+23]), "+f"(d[O+24]), "+f"(d[O+25]), "+f"(d[O+26]), "+f"(d[O+27]), "+f"(d[O+28]), "+f"(d[O+29]), "+f"(d[O+30]), "+f"(d[O+31]), "+f"(d[O+32]), "+f"(d[O+33]), "+f"(d[O+34]), "+f"(d[O+35]), "+f"(d[O+36]), "+f"(d[O+37]), "+f"(d[O+38]), "+f"(d[O+39]), "+f"(d[O+40]), "+f"(d[O+41]), "+f"(d[O+42]), "+f"(d[O+43]), "+f"(d[O+44]), "+f"(d[O+45]), "+f"(d[O+46]), "+f"(d[O+47]), "+f"(d[O+48]), "+f"(d[O+49]), "+f"(d[O+50]), "+f"(d[O+51]), "+f"(d[O+52]), "+f"(d[O+53]), "+f"(d[O+54]), "+f"(d[O+55]), "+f"(d[O+56]), "+f"(d[O+57]), "+f"(d[O+58]), "+f"(d[O+59]), "+f"(d[O+60]), "+f"(d[O+61]), "+f"(d[O+62]), "+f"(d[O+63])
   : "l"(da), "l"(db), "n"(TB & 1), "n"(TB >> 1), "r"(sd));
}
template<int O,int TB,int ACC,int NN> __device__ __forceinline__ void mma_rs128(float (&d)[NN], uint32_t a0, uint32_t a1, uint32_t a2, uint32_t a3, uint64_t db, int sd = 0){
  if constexpr (ACC == 1) asm volatile("wgmma.mma_async.sync.aligned.m64n128k16.f32.bf16.bf16 {%0,%1,%2,%3,%4,%5,%6,%7,%8,%9,%10,%11,%12,%13,%14,%15,%16,%17,%18,%19,%20,%21,%22,%23,%24,%25,%26,%27,%28,%29,%30,%31,%32,%33,%34,%35,%36,%37,%38,%39,%40,%41,%42,%43,%44,%45,%46,%47,%48,%49,%50,%51,%52,%53,%54,%55,%56,%57,%58,%59,%60,%61,%62,%63}, {%64,%65,%66,%67}, %68, 1, 1, 1, %69;"
   : "+f"(d[O+0]), "+f"(d[O+1]), "+f"(d[O+2]), "+f"(d[O+3]), "+f"(d[O+4]), "+f"(d[O+5]), "+f"(d[O+6]), "+f"(d[O+7]), "+f"(d[O+8]), "+f"(d[O+9]), "+f"(d[O+10]), "+f"(d[O+11]), "+f"(d[O+12]), "+f"(d[O+13]), "+f"(d[O+14]), "+f"(d[O+15]), "+f"(d[O+16]), "+f"(d[O+17]), "+f"(d[O+18]), "+f"(d[O+19]), "+f"(d[O+20]), "+f"(d[O+21]), "+f"(d[O+22]), "+f"(d[O+23]), "+f"(d[O+24]), "+f"(d[O+25]), "+f"(d[O+26]), "+f"(d[O+27]), "+f"(d[O+28]), "+f"(d[O+29]), "+f"(d[O+30]), "+f"(d[O+31]), "+f"(d[O+32]), "+f"(d[O+33]), "+f"(d[O+34]), "+f"(d[O+35]), "+f"(d[O+36]), "+f"(d[O+37]), "+f"(d[O+38]), "+f"(d[O+39]), "+f"(d[O+40]), "+f"(d[O+41]), "+f"(d[O+42]), "+f"(d[O+43]), "+f"(d[O+44]), "+f"(d[O+45]), "+f"(d[O+46]), "+f"(d[O+47]), "+f"(d[O+48]), "+f"(d[O+49]), "+f"(d[O+50]), "+f"(d[O+51]), "+f"(d[O+52]), "+f"(d[O+53]), "+f"(d[O+54]), "+f"(d[O+55]), "+f"(d[O+56]), "+f"(d[O+57]), "+f"(d[O+58]), "+f"(d[O+59]), "+f"(d[O+60]), "+f"(d[O+61]), "+f"(d[O+62]), "+f"(d[O+63])
   : "r"(a0), "r"(a1), "r"(a2), "r"(a3), "l"(db), "n"(TB));
  else if constexpr (ACC == 0) asm volatile("wgmma.mma_async.sync.aligned.m64n128k16.f32.bf16.bf16 {%0,%1,%2,%3,%4,%5,%6,%7,%8,%9,%10,%11,%12,%13,%14,%15,%16,%17,%18,%19,%20,%21,%22,%23,%24,%25,%26,%27,%28,%29,%30,%31,%32,%33,%34,%35,%36,%37,%38,%39,%40,%41,%42,%43,%44,%45,%46,%47,%48,%49,%50,%51,%52,%53,%54,%55,%56,%57,%58,%59,%60,%61,%62,%63}, {%64,%65,%66,%67}, %68, 0, 1, 1, %69;"
   : "=f"(d[O+0]), "=f"(d[O+1]), "=f"(d[O+2]), "=f"(d[O+3]), "=f"(d[O+4]), "=f"(d[O+5]), "=f"(d[O+6]), "=f"(d[O+7]), "=f"(d[O+8]), "=f"(d[O+9]), "=f"(d[O+10]), "=f"(d[O+11]), "=f"(d[O+12]), "=f"(d[O+13]), "=f"(d[O+14]), "=f"(d[O+15]), "=f"(d[O+16]), "=f"(d[O+17]), "=f"(d[O+18]), "=f"(d[O+19]), "=f"(d[O+20]), "=f"(d[O+21]), "=f"(d[O+22]), "=f"(d[O+23]), "=f"(d[O+24]), "=f"(d[O+25]), "=f"(d[O+26]), "=f"(d[O+27]), "=f"(d[O+28]), "=f"(d[O+29]), "=f"(d[O+30]), "=f"(d[O+31]), "=f"(d[O+32]), "=f"(d[O+33]), "=f"(d[O+34]), "=f"(d[O+35]), "=f"(d[O+36]), "=f"(d[O+37]), "=f"(d[O+38]), "=f"(d[O+39]), "=f"(d[O+40]), "=f"(d[O+41]), "=f"(d[O+42]), "=f"(d[O+43]), "=f"(d[O+44]), "=f"(d[O+45]), "=f"(d[O+46]), "=f"(d[O+47]), "=f"(d[O+48]), "=f"(d[O+49]), "=f"(d[O+50]), "=f"(d[O+51]), "=f"(d[O+52]), "=f"(d[O+53]), "=f"(d[O+54]), "=f"(d[O+55]), "=f"(d[O+56]), "=f"(d[O+57]), "=f"(d[O+58]), "=f"(d[O+59]), "=f"(d[O+60]), "=f"(d[O+61]), "=f"(d[O+62]), "=f"(d[O+63])
   : "r"(a0), "r"(a1), "r"(a2), "r"(a3), "l"(db), "n"(TB));
  else asm volatile("{\n.reg .pred p;\nsetp.ne.b32 p, %70, 0;\nwgmma.mma_async.sync.aligned.m64n128k16.f32.bf16.bf16 {%0,%1,%2,%3,%4,%5,%6,%7,%8,%9,%10,%11,%12,%13,%14,%15,%16,%17,%18,%19,%20,%21,%22,%23,%24,%25,%26,%27,%28,%29,%30,%31,%32,%33,%34,%35,%36,%37,%38,%39,%40,%41,%42,%43,%44,%45,%46,%47,%48,%49,%50,%51,%52,%53,%54,%55,%56,%57,%58,%59,%60,%61,%62,%63}, {%64,%65,%66,%67}, %68, p, 1, 1, %69;\n}"
   : "+f"(d[O+0]), "+f"(d[O+1]), "+f"(d[O+2]), "+f"(d[O+3]), "+f"(d[O+4]), "+f"(d[O+5]), "+f"(d[O+6]), "+f"(d[O+7]), "+f"(d[O+8]), "+f"(d[O+9]), "+f"(d[O+10]), "+f"(d[O+11]), "+f"(d[O+12]), "+f"(d[O+13]), "+f"(d[O+14]), "+f"(d[O+15]), "+f"(d[O+16]), "+f"(d[O+17]), "+f"(d[O+18]), "+f"(d[O+19]), "+f"(d[O+20]), "+f"(d[O+21]), "+f"(d[O+22]), "+f"(d[O+23]), "+f"(d[O+24]), "+f"(d[O+25]), "+f"(d[O+26]), "+f"(d[O+27]), "+f"(d[O+28]), "+f"(d[O+29]), "+f"(d[O+30]), "+f"(d[O+31]), "+f"(d[O+32]), "+f"(d[O+33]), "+f"(d[O+34]), "+f"(d[O+35]), "+f"(d[O+36]), "+f"(d[O+37]), "+f"(d[O+38]), "+f"(d[O+39]), "+f"(d[O+40]), "+f"(d[O+41]), "+f"(d[O+42]), "+f"(d[O+43]), "+f"(d[O+44]), "+f"(d[O+45]), "+f"(d[O+46]), "+f"(d[O+47]), "+f"(d[O+48]), "+f"(d[O+49]), "+f"(d[O+50]), "+f"(d[O+51]), "+f"(d[O+52]), "+f"(d[O+53]), "+f"(d[O+54]), "+f"(d[O+55]), "+f"(d[O+56]), "+f"(d[O+57]), "+f"(d[O+58]), "+f"(d[O+59]), "+f"(d[O+60]), "+f"(d[O+61]), "+f"(d[O+62]), "+f"(d[O+63])
   : "r"(a0), "r"(a1), "r"(a2), "r"(a3), "l"(db), "n"(TB), "r"(sd));
}

#define NEARLY 0
#define XAHEAD 3
#define HEADN 6
#define WBATCH 1
#define WB 8
#define WSLEEP 20
#define XSPREAD 4
#define NOSEND 0
#define MSPLIT 2
#define PFALL 1
#define L2PF 0
#define STAG 2
#define EPF 2
#define XNB 2
#define FNB 0
#define GNB 0
#define TH 4
#define PF0 4
#define FSPLIT 1
#define MGLU 1
#define SPC 2
#define TL 14
#define GKB 4
#define T0A 8
#define TGATE 1
#define ZLATE 0
#define EARLYADD 0
#define OA 2
#define OB 11
#define EB 9
#define SPACE 100
#define WPF 1
#define WAFTER 7
#define WPACE 0
#define GATE_AT 4
#define TPACE 40
#define PFMODE 0
#define MAPMODE 1
template <int V> struct IC { static constexpr int value = V; };
struct Maps { CUtensorMap x, ft, g64, u64, e, wr, wi, xs, ts, t, g32, u32, d224, fg; };

constexpr int NCTA = 130;
constexpr int U = 16384;
constexpr int TB = 36864;
constexpr int OFF_RING = 8 * U, OFF_Z = 12 * U, OFF_XB = 12 * U, OFF_T = 13 * U, OFF_D = OFF_T;
constexpr int OFF_BAR = 14 * U, OFF_SP = OFF_BAR + 512, OFF_G = OFF_SP + 1024 + 128;
constexpr int SMEM_BYTES = OFF_G + 512;
constexpr int B_FX = 0, B_FA = 8, B_FT = 12, B_Z = 16, B_W = 24, B_HX = 25, B_TL = 26, B_HP = 27, B_WR = 31, B_E0 = 35;
constexpr int B_EA = 36, B_ET = 40, B_PZ = 44, B_RDY = 46, B_FE = 47;
constexpr int B_T = 51, B_XS = 52, B_G = 54, B_RD0 = 55, NBAR = 56;
__host__ __device__ constexpr int rslot(int n) { return n & 3; }
__host__ __device__ constexpr int rpar(int n) { return (n >> 2) & 1; }

__global__ void __cluster_dims__(2, 1, 1) __launch_bounds__(512, 1)
fused_kernel(Work* __restrict__ ws, const uint16_t* __restrict__ dtab, const __nv_bfloat16* __restrict__ w_r, const __nv_bfloat16* __restrict__ w_i,
             const __nv_bfloat16* __restrict__ gate_w, const __nv_bfloat16* __restrict__ x, __nv_bfloat16* __restrict__ out,
             const __grid_constant__ Maps maps) {
  extern __shared__ __align__(1024) uint8_t smem[];
  if (threadIdx.x < 32 && elect_one()) {
#pragma unroll
    for (int i = 0; i < PF0; i++) asm volatile("prefetch.tensormap [%0];" ::"l"((const char*)&maps + i * 128) : "memory");
  }
  const uint32_t sb = smem_u32(smem);
  const uint32_t bars = sb + OFF_BAR;
  const int tid = threadIdx.x, lane = tid & 31;
  const int warp = __shfl_sync(0xffffffffu, tid >> 5, 0);
  const bool helper = blockIdx.x >= 128;
  const int cl = (blockIdx.x >> 1) & 63, rank = blockIdx.x & 1;
  const int q4 = (cl & 1) | ((cl >> 2) & 2), rb = ((cl >> 1) & 3) | ((cl >> 4) << 2);
  const int j = 2 * q4 + rank;
  const int f_full = 448 * q4 + (rank ? 256 : 0);
  const int f_half = 448 * q4 + (rank ? 224 : 192);
  const int kg = 2 * j + (rb >> 3), tn = rb & 7;

  if (tid == 64) { PROF_EV(0); PROF_CK(40); }
  if (warp < 8) {
    if (!helper && tid < 32) {
      const int r = 16 * j + (tid & 15);
      asm volatile("prefetch.global.L2 [%0];" ::"l"(x + (size_t)(2 * rb + (r >> 6) + 32 * (r & 63)) * 512 + 64 * (tid >> 4)));
    }
    asm volatile("barrier.cluster.arrive.relaxed.aligned;" ::: "memory");
    asm volatile("setmaxnreg.inc.sync.aligned.u32 192;");
    if (!helper) {
      const int wg = warp >> 2, w = warp & 3, g = lane >> 2;
      const bool elect = (tid & 127) == 0;
      float cX[32], cA[64], cB[64], cC[64], ci[64], ct[64];
      const int zero = blockIdx.x >> 16;
      uint32_t h[56], yf[16];
      const uint32_t d0 = (sb & 0x3FFFF) >> 4;
      const uint32_t dK = d0 | (1u << 16), dN = d0 | (512u << 16);
      const uint32_t dX = dK + wg * 512;
      constexpr uint32_t RING = OFF_RING >> 4;
      auto waitA = [&](int n) { mbar_wait(bars + 8 * (B_FA + rslot(n)), rpar(n)); };
      auto freeA = [&](int n) { mbar_arrive_if(elect, bars + 8 * (B_EA + rslot(n))); };
      auto nop = [] {};

      asm volatile("bar.sync 0, 384;" ::: "memory");
#pragma unroll 1
      for (int i = 0; i < 4; i++) {
        const uint64_t dx = d128(dX + i * 2048), df = d128(dK + (OFF_XB >> 4) + (i & 1) * 1024);
        mbar_wait(bars + 8 * (B_FX + 2 * i), 0);
        wg_fence();
        mma_ss64<0, 0, 2>(cX, df, dx, i);
        mma_ss64<0, 0, 1>(cX, df + 2, dx + 2);
        wg_commit(); wg_wait<1>();
        mbar_arrive_if(elect && i, bars + 8 * (B_EA + rslot(i - 1)));
        mma_ss64<0, 0, 1>(cX, df + 4, dx + 4);
        mma_ss64<0, 0, 1>(cX, df + 6, dx + 6);
        if (i == 0 && tid == 0) PROF_EV(1);
        mbar_wait(bars + 8 * (B_FX + 2 * i + 1), 0);
        wg_fence();
#pragma unroll
        for (int k = 0; k < 4; k++) mma_ss64<0, 0, 1>(cX, df + (512 + k * 2), dx + (1024 + k * 2));
        wg_commit();
        waitA(i);
        wg_fence();
        const uint64_t da = d128(dX + i * 1024), db = d128(dN + RING + i * 1024);
        mma_ss128<0, 1, 2>(cA, da, db, i);
        wg_commit(); wg_wait<1>();
        mbar_arrive_if(elect, bars + 8 * (B_FE + i));
#pragma unroll
        for (int k = 1; k < 4; k++) mma_ss128<0, 1, 1>(cA, da + k * 2, db + k * 128);
        wg_commit();
      }
      fence_regs<0, 32>(cX);
#pragma unroll
      for (int e = 0; e < 16; e++) yf[e] = pack_pin(cX[2 * e], cX[2 * e + 1]);
      if (tid == 0) { PROF_EV(2); PROF_CK(42); }
      {
        waitA(4); mbar_wait(bars + 8 * B_E0, 0);
        const uint64_t de = d128(dN + (wg ? RING : OFF_XB >> 4));
        wg_fence();
        mma_rs128<0, 1, 0>(cB, yf[0], yf[1], yf[2], yf[3], de);
        wg_commit();
        wg_wait<1>();
        freeA(3);
#pragma unroll
        for (int k = 1; k < 4; k++) mma_rs128<0, 1, 1>(cB, yf[4 * k], yf[4 * k + 1], yf[4 * k + 2], yf[4 * k + 3], de + k * 128);
        wg_commit();
      }
      bool rel = false;
      auto acquire = [&](int n) {
        rel = elect;
        if (!mbar_try(bars + 8 * (B_FA + rslot(n)), rpar(n))) { wg_wait<0>(); freeA(n - 1); rel = false; waitA(n); }
      };
      auto freeP = [&](int n) { mbar_arrive_if(rel, bars + 8 * (B_EA + rslot(n - 1))); };
      auto ffn_step = [&](auto first, auto split, float (&acc)[64], int n, int kb, auto done, auto work) {
        constexpr int SPLIT = decltype(split)::value;
        acquire(n);
        wg_fence();
        const uint64_t dx = d128(dX + kb * 1024), db = d128(dN + RING + rslot(n) * 1024);
        mma_ss128<0, 1, decltype(first)::value>(acc, dx, db, kb);
#pragma unroll
        for (int k = 1; k < SPLIT; k++) mma_ss128<0, 1, 1>(acc, dx + k * 2, db + k * 128);
        wg_commit();
        work();
        wg_wait<1>();
        freeP(n);
        done();
        if (SPLIT < 4) {
          wg_fence();
#pragma unroll
          for (int k = SPLIT; k < 4; k++) mma_ss128<0, 1, 1>(acc, dx + k * 2, db + k * 128);
          wg_commit();
        }
      };
      {
        const int s0 = 2 * rb + wg, kr = 2 * (s0 & 3);
        const int m = lane >> 3, r = lane & 7;
        const uint32_t a0 = sb + OFF_XB + wg * 8192 + (((w >> 1) * 8 + (m >> 1)) * 2 + (w & 1)) * 256 + (m & 1) * 128 + ((r ^ (kr + (m & 1))) << 4);
        ffn_step(IC<1>(), IC<4>(), cA, 5, 4, [&] { fence_regs<0, 64>(cB); }, nop);
        asm volatile("bar.sync 5, 256;" ::: "memory");
        auto stage = [&](int i) {
          stsm4t(a0 + i * 1024, pack_bf16(cB[8 * i] - cB[34 + 8 * i], cB[8 * i + 1] - cB[35 + 8 * i]),
                 pack_bf16(cB[32 + 8 * i] + cB[8 * i + 2], cB[33 + 8 * i] + cB[8 * i + 3]),
                 pack_bf16(cB[8 * i + 4] - cB[38 + 8 * i], cB[8 * i + 5] - cB[39 + 8 * i]),
                 pack_bf16(cB[36 + 8 * i] + cB[8 * i + 6], cB[37 + 8 * i] + cB[8 * i + 7]));
          if (j == 0 && w == 0) {
            const uint32_t a1 = r ? sb + OFF_SP + 1024 : sb + OFF_SP + wg * 512 + (m & 1) * 256 + (m >> 1) * 128;
#pragma unroll
            for (int n = 2 * i; n < 2 * i + 2; n++)
              asm volatile("stmatrix.sync.aligned.m8n8.x4.shared.b16 [%0], {%1,%2,%3,%4};" ::"r"(a1 + ((n ^ (kr + (m >> 1)) ^ r) << 4)),
                           "r"(pack_bf16(cB[4 * n], cB[4 * n + 1])), "r"(pack_bf16(cB[4 * n + 2], cB[4 * n + 3])),
                           "r"(pack_bf16(cB[32 + 4 * n], cB[33 + 4 * n])), "r"(pack_bf16(cB[34 + 4 * n], cB[35 + 4 * n])) : "memory");
          }
        };
        auto publish = [&] {
          asm volatile("fence.proxy.async.shared::cta;" ::: "memory");
          __syncwarp();
          mbar_arrive_if(lane == 0, bars + 8 * (B_XS + wg));
          if (tid == 0) PROF_EV(3);
        };
        stage(0);
        ffn_step(IC<1>(), IC<FSPLIT>(), cA, 6, 5, nop, nop);
        stage(1);
        ffn_step(IC<1>(), IC<FSPLIT>(), cA, 7, 6, nop, nop);
        stage(2);
        ffn_step(IC<1>(), IC<2>(), cA, 8, 7, [&] { stage(3); }, nop);
        publish();
      }
      uint32_t gb0 = 0, gb1 = 0;
      uint32_t ob[2] = {0, 0};
      auto glu = [&](auto& acc, int half, int ho, int i0, int i1) {
#pragma unroll
        for (int i = i0; i < i1; i++)
          asm volatile("{\n.reg .b32 a, b;\ncvt.rn.relu.bf16x2.f32 a, %2, %1;\ncvt.rn.bf16x2.f32 b, %4, %3;\nmul.rn.bf16x2 a, a, b;\nmul.rn.bf16x2 %0, a, %5;\n}"
                       : "=r"(h[ho + i]) : "f"(acc[2 * i]), "f"(acc[2 * i + 1]), "f"(acc[half + 2 * i]), "f"(acc[half + 1 + 2 * i]), "r"(ob[i & 1]) : "memory");
      };
      ffn_step(IC<2>(), IC<1>(), cB, 9, zero, nop, nop);
#pragma unroll 1
      for (int kb = 1; kb < 8; kb++)
        ffn_step(IC<1>(), IC<FSPLIT>(), cB, 9 + kb, kb, nop, [&] {
          if (kb == GKB) {
            mbar_wait(bars + 8 * B_G, 0);
            asm volatile("ld.shared.u32 %0, [%2];\nld.shared.u32 %1, [%2+32];" : "=r"(gb0), "=r"(gb1) : "r"(sb + OFF_G + (wg * 64 + w * 16 + g) * 4) : "memory");
          } else if (kb == 5 + 2 * wg) {
            ob[0] = pack_bf16(1.0f - bf_hi(gb0), 1.0f - bf_hi(gb0)); ob[1] = pack_bf16(1.0f - bf_hi(gb1), 1.0f - bf_hi(gb1));
            glu(cA, 32, 0, 0, 16);
          }
        });
      const uint32_t tag = gb0 & 1;
      const float g0 = bf_hi(gb0), g1 = bf_hi(gb1);
      if (tid == 0) { PROF_EV(4); PROF_CK(43); }
      auto m_step = [&](auto first, int i) {
        acquire(17 + i);
        wg_fence();
        const uint64_t dx = d128(dX + i * 2048), dm = d64(dN + RING + rslot(17 + i) * 1024);
        mma_ss64<0, 1, decltype(first)::value>(ct, dx, dm);
#pragma unroll
        for (int k = 1; k < MSPLIT; k++) mma_ss64<0, 1, 1>(ct, dx + ((k >> 2) * 1024 + (k & 3) * 2), dm + k * 64);
        wg_commit();
        wg_wait<1>();
        freeP(17 + i);
        wg_fence();
#pragma unroll
        for (int k = MSPLIT; k < 8; k++) mma_ss64<0, 1, 1>(ct, dx + ((k >> 2) * 1024 + (k & 3) * 2), dm + k * 64);
        wg_commit();
      };
      m_step(IC<0>(), 0);
#pragma unroll 1
      for (int i = 1; i < 5; i++) {
        if (i == 1 + 2 * wg) glu(cB, 32, 16, 0, 16);
        if (i < 4) m_step(IC<1>(), i);
      }
      if (tid == 0) { PROF_EV(5); PROF_CK(44); }
      ffn_step(IC<0>(), IC<1>(), cC, 21, 0, nop, nop);
#pragma unroll 1
      for (int kb = 1; kb < 8; kb++)
        ffn_step(IC<1>(), IC<FSPLIT>(), cC, 21 + kb, kb, [&] { mbar_arrive_if(elect && !(kb & 1), bars + 8 * (B_ET + (kb >> 1) - 1)); }, [&] {
          if (kb == 1 + wg) glu(ct, 16, 48, 0, 8);
        });

      auto twait = [&](uint32_t bar, uint32_t par, int) { mbar_wait(bar, par); };
      const int fo = warp * 128 + lane;
      auto fetch = [&](uint4 (&pv)[4], int z) {
        twait(bars + 8 * (z < 4 ? B_Z + 2 * z + wg : z < 6 ? B_HP + z - 4 : B_HP + 2 + wg), 0, 8 + z);
        const uint8_t* src = smem + (z < 4 ? OFF_Z - z * U : z == 4 ? OFF_T : (z - 5) * U) + fo * 16;
#pragma unroll
        for (int i = 0; i < 4; i++) pv[i] = *(const uint4*)(src + i * 512);
      };
      const uint32_t peerZ = mapa(sb + OFF_Z + fo * 16, rank ^ 1), peerB = mapa(bars + 8 * (B_Z + wg), rank ^ 1);
      auto tile_mma = [&](auto off, int t, int k0, int k1) {
        constexpr int O = decltype(off)::value;
        const uint64_t db = d128(dN + (t & 3) * (TB >> 4)), dw = db + rank * 256, dm = db + (rank ? 0 : 1536);
#pragma unroll
        for (int k = k0; k < k1; k++) {
          if (k == 0 && O == 0) mma_rs64<O, 1, 2>(ct, h[0], h[1], h[2], h[3], dw, zero);
          else if (k < 14) mma_rs64<O, 1, 1>(ct, h[4 * k], h[4 * k + 1], h[4 * k + 2], h[4 * k + 3], k < 12 ? dw + k * 128 : dm + (k - 12) * 128);
          else if (k == 14) mma_rs64<O, 1, 2>(ct, yf[0], yf[1], yf[2], yf[3], db + k * 128, zero);
          else mma_rs64<O, 1, 1>(ct, yf[4 * k - 56], yf[4 * k - 55], yf[4 * k - 54], yf[4 * k - 53], db + k * 128);
        }
      };
      uint4 pv[4];
      const float sgn = rank ? -1.0f : 1.0f;
      auto odd_head = [&](int t) {
        twait(bars + 8 * (B_FT + (t & 3)), t >> 2, t);
        wg_fence();
        tile_mma(IC<32>(), t, 14, 18);
        wg_commit();
        if (t < 4) twait(bars + 8 * (t == 1 ? B_RD0 : B_RDY), 0, 14 + t);
        wg_wait<0>();
        mbar_arrive_if(elect && t < 6, bars + 8 * (B_ET + t - 1));
        fence_regs<0, 64>(ct);
#pragma unroll
        for (int i = 0; i < 4; i++) {
          uint32_t u[4];
#pragma unroll
          for (int e = 0; e < 4; e++) u[e] = pack_pin(fmaf(sgn, ct[32 + 8 * i + 2 * e], ct[8 * i + 2 * e]), fmaf(sgn, ct[33 + 8 * i + 2 * e], ct[8 * i + 2 * e + 1]));
          pv[i] = make_uint4(u[0], u[1], u[2], u[3]);
        }
        wg_fence();
        tile_mma(IC<32>(), t, 0, OA);
#pragma unroll
        for (int i = 0; i < 4; i++) {
          asm volatile("st.async.weak.shared::cluster.mbarrier::complete_tx::bytes.v4.b32 [%0], {%2,%3,%4,%5}, [%1];" ::"r"(peerZ - (t >> 1) * U + i * 512),
                       "r"(peerB + 16 * (t >> 1)), "r"(pv[i].x), "r"(pv[i].y), "r"(pv[i].z), "r"(pv[i].w) : "memory");
          tile_mma(IC<32>(), t, OA + i, OA + i + 1);
        }
        wg_commit();
      };
      asm volatile("barrier.cluster.wait.aligned;" ::: "memory");
      twait(bars + 8 * B_FT, 0, 0);
      if (wg) asm volatile("bar.sync 6, 256;" ::: "memory");
      wg_fence();
      tile_mma(IC<0>(), 0, 0, T0A);
      wg_commit();
      waitA(29 + wg);
      wg_wait<1>();
      mbar_arrive_if(elect, bars + 8 * (B_ET + 3));
      glu(cC, 32, 32, 0, 16);
      if (tid == 0) PROF_EV(6);
      if (tid == 128) PROF_EV(27);
      mbar_wait(bars + 8 * (j == 0 ? B_T : B_TL), 0);
      if (tid == 0) { PROF_EV(7); PROF_CK(45); }
      wg_fence();
      {
        const uint64_t dt = d128(dN + (OFF_T >> 4) + wg * 512), de = d128(dK + RING + (1 + wg) * 1024);
        mma_ss64<0, 1, 0>(ci, de, dt);
        mma_ss64<32, 1, 0>(ci, de + 512, dt);
#pragma unroll
        for (int k = 1; k < 4; k++) {
          mma_ss64<0, 1, 1>(ci, de + k * 2, dt + k * 128);
          mma_ss64<32, 1, 1>(ci, de + (512 + k * 2), dt + k * 128);
        }
        wg_commit();
      }
      tile_mma(IC<0>(), 0, T0A, 14);
      wg_commit();
      if (!wg) asm volatile("bar.arrive 6, 256;" ::: "memory");
      wg_wait<1>();
      if (elect) asm volatile("mbarrier.arrive.shared::cluster.b64 _, [%0];" ::"r"(mapa(bars + 8 * B_RDY, rank ^ 1)) : "memory");
      mbar_arrive_if(elect, bars + 8 * (B_PZ + 1));
      fence_regs<0, 64>(ci);
#pragma unroll
      for (int i = 0; i < 16; i++) {
        const float gg = ((i & 1) ? g1 : g0) * (2.0f / (2048.0f * 512.0f));
        if (i & 2) yf[i] = pack_pin((ci[2 * i] - ci[28 + 2 * i]) * gg, (ci[2 * i + 1] - ci[29 + 2 * i]) * gg);
        else yf[i] = pack_pin((ci[2 * i] + ci[36 + 2 * i]) * gg, (ci[2 * i + 1] + ci[37 + 2 * i]) * gg);
      }
      if (tid == 0) PROF_EV(8);
      if (tid == 128) PROF_EV(28);
#pragma unroll 1
      for (int t = 1; t < 7; t += 2) {
        odd_head(t);
        wg_fence();
        tile_mma(IC<32>(), t, OA + 4, 14);
        wg_commit();
        const int zo = t >> 1, owner = rb * 8 + 2 * ((q4 + zo + 1) & 3) + rank;
        uint4* dst = ws->part + (size_t)(owner * 3 + zo) * 1024 + fo;
        auto send = [&] {
          fence_regs<32, 32>(ct);
#pragma unroll
          for (int i = 0; i < 4; i++)
            asm volatile("st.relaxed.gpu.global.v4.u32 [%0], {%1,%2,%3,%4};" ::"l"(dst + i * 32),
                         "r"((add_bf2(pv[i].x, pack_bf16(ct[32 + 8 * i], ct[33 + 8 * i])) & ~1u) | tag), "r"(add_bf2(pv[i].y, pack_bf16(ct[34 + 8 * i], ct[35 + 8 * i]))),
                         "r"(add_bf2(pv[i].z, pack_bf16(ct[36 + 8 * i], ct[37 + 8 * i]))), "r"(add_bf2(pv[i].w, pack_bf16(ct[38 + 8 * i], ct[39 + 8 * i]))) : "memory");
          hint_add_if(lane == 0, &ws->cntP[32 * owner + 8 * (zo + (zo == 2 ? wg : 0))]);
        };
        if (t == 5) fetch(pv, 2);
        twait(bars + 8 * (B_FT + ((t + 1) & 3)), (t + 1) >> 2, t + 1);
        wg_fence();
        tile_mma(IC<0>(), t + 1, 0, TH);
        wg_commit();
        wg_wait<1>();
        mbar_arrive_if(elect && t < 5, bars + 8 * (B_ET + t));
        if (t == 5) send(); else fetch(pv, zo);
        wg_fence();
        tile_mma(IC<0>(), t + 1, TH, EB);
        wg_commit();
        if (t != 5) send();
        wg_fence();
        tile_mma(IC<0>(), t + 1, EB, 14);
        wg_commit();
      }
      {
        uint4 p1[4], p2[4];
        auto acc4 = [&](uint4 (&d)[4], const uint4 (&a)[4]) {
#pragma unroll
          for (int i = 0; i < 4; i++) { d[i].x = add_bf2(d[i].x, a[i].x); d[i].y = add_bf2(d[i].y, a[i].y); d[i].z = add_bf2(d[i].z, a[i].z); d[i].w = add_bf2(d[i].w, a[i].w); }
        };
        auto add32 = [&](const uint4 (&a)[4]) {
#pragma unroll
          for (int i = 0; i < 4; i++) {
            const uint32_t u[4] = {a[i].x, a[i].y, a[i].z, a[i].w};
#pragma unroll
            for (int e = 0; e < 4; e++) { ct[32 + 8 * i + 2 * e] += bf_lo(u[e]); ct[33 + 8 * i + 2 * e] += bf_hi(u[e]); }
          }
        };
        odd_head(7);
        fetch(pv, 4);
        fetch(p1, 5);
        wg_fence();
        tile_mma(IC<32>(), 7, OA + 4, OB);
        wg_commit();
        uint32_t bad = 0;
#pragma unroll
        for (int i = 0; i < 4; i++) { bad |= (pv[i].x ^ tag) | (p1[i].x ^ tag); pv[i].x &= ~1u; p1[i].x &= ~1u; }
        acc4(pv, p1);
        fetch(p1, 3);
        wg_fence();
        tile_mma(IC<32>(), 7, OB, 14);
        wg_commit();
        if (tid == 0) { PROF_EV(9); PROF_CK(46); }
        if (tid == 128) PROF_EV(29);
        fetch(p2, 6);
        if (tid == 0) PROF_EV(24);
        wg_wait<0>();
        fence_regs<32, 32>(ct);
#pragma unroll
        for (int i = 0; i < 4; i++) bad |= p2[i].x ^ tag;
        if (__any_sync(0xffffffffu, bad & 1)) {
          const uint4* src = ws->part + (size_t)(rb * 8 + j) * 3 * 1024 + fo;
          uint4 p0[4];
          int n = 0;
          do {
            bad = 0;
#pragma unroll
            for (int i = 0; i < 4; i++) {
              pv[i] = ld_x4(src + i * 32); p0[i] = ld_x4(src + 1024 + i * 32); p2[i] = ld_x4(src + 2048 + i * 32);
              bad |= (pv[i].x ^ tag) | (p0[i].x ^ tag) | (p2[i].x ^ tag);
            }
            if (++n > (1 << 21)) __trap();
          } while (__any_sync(0xffffffffu, bad & 1));
#pragma unroll
          for (int i = 0; i < 4; i++) { pv[i].x &= ~1u; p0[i].x &= ~1u; }
          acc4(pv, p0);
        }
#pragma unroll
        for (int i = 0; i < 4; i++) p2[i].x &= ~1u;
        acc4(p1, p2);
        add32(pv); add32(p1);
#pragma unroll
        for (int i = 0; i < 4; i++)
          pv[i] = make_uint4(pack_bf16(ct[32 + 8 * i], ct[33 + 8 * i]), pack_bf16(ct[34 + 8 * i], ct[35 + 8 * i]), pack_bf16(ct[36 + 8 * i], ct[37 + 8 * i]), pack_bf16(ct[38 + 8 * i], ct[39 + 8 * i]));
        if (tid == 0) PROF_EV(14);
        const uint32_t stg = sb + OFF_T + warp * 2048;
        const int mr = (lane & 7) + ((lane >> 3) & 1) * 8, mc = lane >> 4;
#pragma unroll
        for (int i = 0; i < 4; i++)
          asm volatile("stmatrix.sync.aligned.m8n8.x4.shared.b16 [%0], {%1,%2,%3,%4};" ::"r"(stg + mr * 128 + (((2 * i + mc) ^ (mr & 7)) << 4)), "r"(pv[i].x),
                       "r"(pv[i].y), "r"(pv[i].z), "r"(pv[i].w) : "memory");
        __syncwarp();
#pragma unroll
        for (int i = 0; i < 4; i++) {
          const int r = 4 * i + (lane >> 3), c = lane & 7;
          const uint4 v = *(const uint4*)(smem + OFF_T + warp * 2048 + r * 128 + ((c ^ (r & 7)) << 4));
          *(uint4*)(out + (size_t)(2 * rb + wg + 32 * (16 * w + r)) * 512 + 64 * (q4 + 4 * rank) + 8 * c) = v;
        }
      }
      if (tid == 0) { PROF_EV(15); PROF_CK(41); }
      if (tid == 128) PROF_EV(30);
    }
  } else if (warp < 12) {
    asm volatile("setmaxnreg.dec.sync.aligned.u32 104;");
    asm volatile("barrier.cluster.arrive.relaxed.aligned;" ::: "memory");
    const int t = tid - 256, w = warp - 8;
    const uint32_t ep = ld_x1(&ws->epoch[blockIdx.x * 8]);
    const uint32_t tag = (ep + 1) & 1;
    auto w_issue = [&](const CUtensorMap* m) {

      if (elect_one()) { mbar_expect_tx(bars + 8 * (B_WR + w), 3072); tma4d(sb + OFF_T + w * 3072, m, bars + 8 * (B_WR + w), 16 * kg, 0, 2 * w, tn); }

          __syncwarp();
    };
    auto gate_rows = [&] {
      const int r = 16 * j + 4 * w + (lane >> 3);
      const uint4* pg = (const uint4*)gate_w + (lane & 7);
      {
        float a = 0.f;
        asm volatile("bar.sync 4, 256;" ::: "memory");
#pragma unroll 1
        for (int hf = 0; hf < 2; hf++) {
          uint4 v[4], u[4];
#pragma unroll
          for (int kb = 0; kb < 4; kb++) v[kb] = __ldg(pg + (4 * hf + kb) * 8);
          mbar_wait(bars + 8 * (B_FE + 1 + 2 * hf), 0);
          if (hf) w_issue(&maps.wr);
#pragma unroll
          for (int kb = 0; kb < 4; kb++) u[kb] = *(const uint4*)(smem + (4 * hf + kb) * U + r * 128 + (((lane ^ r) & 7) << 4));
#pragma unroll
          for (int kb = 0; kb < 4; kb++) {
            const uint32_t uu[4] = {u[kb].x, u[kb].y, u[kb].z, u[kb].w}, vv[4] = {v[kb].x, v[kb].y, v[kb].z, v[kb].w};
#pragma unroll
            for (int e = 0; e < 4; e++) {
              uint32_t pr;
              asm("mul.rn.bf16x2 %0, %1, %2;" : "=r"(pr) : "r"(uu[e]), "r"(vv[e]));
              a += bf_lo(pr) + bf_hi(pr);
            }
          }
        }
#pragma unroll
        for (int o = 4; o; o >>= 1) a += __shfl_xor_sync(0xffffffffu, a, o);
        if ((lane & 7) == 0)
          asm volatile("st.relaxed.gpu.global.u32 [%0], %1;" ::"l"(ws->gate + rb * 128 + r),
                       "r"(pack_bf16(0.f, __fdividef(1.0f, 1.0f + __expf(-bf_lo(pack_bf16(a, 0.f))))) | tag) : "memory");
        if (t == 0) PROF_EV(18);
      }
    };
    {
      const int g = lane >> 2, q = lane & 3;
      uint32_t wf[32];
      if (!helper) {
        gate_rows();
        const uint32_t wa = sb + OFF_T + w * (3072 + 4) + q * 48 + g * 4;
#pragma unroll 1
        for (int ri = 0; ri < 2; ri++) {
          mbar_wait(bars + 8 * (B_WR + w), ri);
#pragma unroll
          for (int n2 = 0; n2 < 32 / WB; n2++) {
            uint32_t v[WB];
#pragma unroll
            for (int i = 0; i < WB; i++) {
              const int e = n2 * WB + i;
              asm volatile("ld.shared.u16 %0, [%1];" : "=r"(v[i]) : "r"(wa + ((e >> 1) & 7) * 192 + (e & 1) * (1536 + 2) + (e >> 4) * 2) : "memory");
            }
#pragma unroll
            for (int i = 0; i < WB; i++) wf[n2 * WB + i] = __byte_perm(wf[n2 * WB + i], v[i], 0x5432);
            if (WSLEEP) { asm volatile("nanosleep.u32 %0;" ::"r"(WSLEEP + (v[WB - 1] >> 16)) : "memory"); }
          }
          __syncwarp();
          if (ri == 0) w_issue(&maps.wi);
        }
        asm volatile("bar.sync 1, 128;" ::: "memory");
        if (t == 0) PROF_EV(11);
      } else {
        asm volatile("bar.sync 4, 256;" ::: "memory");
        hint_wait(&ws->cntW[0], (ep + 1) * 128u);
        const uint32_t t0 = (uint32_t)clock();
#pragma unroll 1
        for (;;) {
          uint32_t bad = 0;
#pragma unroll
          for (int i = 0; i < 32; i++) {
            const float2 v = ld_x2((const float2*)ws->Wh + (i >> 4) * 2048 + 16 * w + g + 8 * (i & 1) + 64 * q + ((i >> 1) & 7) * 256);
            wf[i] = __float_as_uint(v.x); bad |= __float_as_uint(v.y) ^ tag;
          }
          if (!__any_sync(0xffffffffu, bad & 1)) break;
          spin_guard(t0);
        }
        if (t == 0) PROF_EV(11);
      }
      if (w == 0 && elect_one()) { mbar_expect_tx(bars + 8 * B_W, 8192); bulk_load(sb + OFF_D, dtab, 8192, bars + 8 * B_W); }
      asm volatile("barrier.cluster.wait.aligned;" ::: "memory");
      mbar_wait(bars + 8 * B_W, 0);
      mbar_wait(bars + 8 * B_HX, 0);
      if (t == 0) PROF_EV(12);
      const uint32_t dd = (sb & 0x3FFFF) >> 4;
      const uint64_t dF = d128((dd + (OFF_D >> 4)) | (512u << 16)), dI = d128((dd + (OFF_D >> 4)) | (1u << 16)), dA = d128((dd + (OFF_XB >> 4)) | (512u << 16));
      float az[32];
      const int zero = blockIdx.x >> 16;
      uint32_t pf[32];
#pragma unroll
      for (int mt = 0; mt < 2; mt++) {
        wg_fence();
        if (mt == 0) mma_ss64<0, 3, 0>(az, dA, dF);
        else mma_ss64<0, 3, 2>(az, dA + 512, dF, zero);
#pragma unroll
        for (int k = 1; k < 4; k++) mma_ss64<0, 3, 1>(az, dA + (mt * 512 + k * 128), dF + k * 128);
        wg_commit();
        wg_wait<0>();
        fence_regs<0, 32>(az);
#pragma unroll
        for (int i = 0; i < 16; i++) {
          const float wr = bf_lo(wf[16 * mt + i]), wi = bf_hi(wf[16 * mt + i]);
          pf[16 * mt + i] = pack_pin(fmaf(az[2 * i], wr, -az[2 * i + 1] * wi), fmaf(az[2 * i], wi, az[2 * i + 1] * wr));
        }
      }
      if (t == 0) PROF_EV(16);
      {
        const int m = lane >> 3;
        const uint32_t a0 = sb + OFF_XB + w * 4096 + (m & 1) * 1024 + (m >> 1) * 128 + (lane & 7) * 16;
        uint32_t pk[16];
#pragma unroll
        for (int mt = 0; mt < 3; mt++) {
          if (mt < 2) {
            wg_fence();
            mma_rs64<0, 0, 2>(az, pf[16 * mt], pf[16 * mt + 1], pf[16 * mt + 2], pf[16 * mt + 3], dI, mt ? (int)helper : zero);
#pragma unroll
            for (int k = 1; k < 4; k++) mma_rs64<0, 0, 1>(az, pf[16 * mt + 4 * k], pf[16 * mt + 4 * k + 1], pf[16 * mt + 4 * k + 2], pf[16 * mt + 4 * k + 3], dI + k * 2);
            wg_commit();
          }
          if (mt > 0 && !helper) {
#pragma unroll
            for (int i = 0; i < 4; i++) stsm4t(a0 + (mt - 1) * 2048 + i * 256, pk[4 * i], pk[4 * i + 1], pk[4 * i + 2], pk[4 * i + 3]);
          }
          if (mt < 2) {
            wg_wait<0>();
            fence_regs<0, 32>(az);
#pragma unroll
            for (int i = 0; i < 16; i++) pk[i] = pack_pin(az[2 * i], az[2 * i + 1]);
          }
        }
      }
      if (helper) {
#pragma unroll
        for (int i = 0; i < 16; i++) {
          const int n = i >> 1, s0 = 4 * n + q;
          if ((n & 1) == (int)(blockIdx.x & 1)) st_u2(ws->Ts + s0 * 64 + 16 * w + g + 8 * (i & 1), pack_bf16(az[2 * i], az[2 * i + 1]), tag);
        }
        __syncwarp();
        hint_add_if(lane == 0, &ws->cntH[0]);
        if (t == 0) { ws->epoch[blockIdx.x * 8] = ep + 1; PROF_EV(13); }
      } else {
        asm volatile("fence.proxy.async.shared::cta;" ::: "memory");
        __syncwarp();
        if (elect_one()) {
          if (t == 0) PROF_EV(17);
          if (SPACE) __nanosleep(SPACE * w);
          asm volatile("cp.async.bulk.tensor.4d.global.shared::cta.bulk_group [%0, {%2, %3, %4, %5}], [%1];" ::"l"(&maps.ts), "r"(sb + OFF_XB + w * 4096),
                       "r"(16 * (kg & 3)), "r"(0), "r"(8 * tn + 2 * w), "r"(2 * q4) : "memory");
          bulk_done_signal(&ws->cntT[32 * q4]);
          asm volatile("mbarrier.arrive.shared::cluster.b64 _, [%0];" ::"r"(mapa(bars + 8 * B_RD0, rank ^ 1)) : "memory");
          if (t == 96) PROF_EV(13);
        }
        __syncwarp();
        if (j == 0) {
          hint_wait(&ws->cntH[0], (ep + 1) * 8u);
          const uint32_t t0 = (uint32_t)clock();
          float2 v;
          do { v = ld_x2((const float2*)ws->Ts + 2 * rb * 64 + t); spin_guard(t0); } while (__any_sync(0xffffffffu, (__float_as_uint(v.y) ^ tag) & 1));
          mbar_wait(bars + 8 * B_TL, 0);
          const uint32_t u = __float_as_uint(v.x);
          *(uint16_t*)(smem + OFF_T + t * 128 + ((t & 7) << 4)) = (uint16_t)u;
          *(uint16_t*)(smem + OFF_T + t * 128 + (((t & 7) ^ 1) << 4)) = (uint16_t)(u >> 16);
          asm volatile("fence.proxy.async.shared::cta;" ::: "memory");
          __syncwarp();
          mbar_arrive_if(lane == 0, bars + 8 * B_T);
        }
      }
    }
  } else {
    asm volatile("setmaxnreg.dec.sync.aligned.u32 24;");
    auto xf_load = [&](int q) {
      const uint32_t fb = bars + 8 * (B_FX + q);
      mbar_expect_tx(fb, U + 8192);
      tma3d(sb + q * U, &maps.x, fb, 64 * q, 0, 2 * rb);
      if (q >= 4) mbar_wait(bars + 8 * (B_FE + ((q - 4) >> 1)), 0);
      tma2d(sb + OFF_XB + (q & 3) * 8192, &maps.ft, fb, 64 * q, 64 * j);
    };
    if (elect_one()) {
      if (warp == 14) {
#pragma unroll
        for (int i = 0; i < B_FT; i++) mbar_init(bars + 8 * i, 1);
        asm volatile("fence.mbarrier_init.release.cluster;" ::: "memory");
        if (!helper) {
#pragma unroll 1
          for (int n = 0; n < 2; n++) {
            const uint32_t fb = bars + 8 * (B_FA + n);
            xf_load(2 * n); xf_load(2 * n + 1);
            mbar_expect_tx(fb, U);
            tma2d(sb + OFF_RING + n * U, &maps.g64, fb, f_full, 64 * n);
            tma2d(sb + OFF_RING + n * U + 8192, &maps.u64, fb, f_full, 64 * n);
          }
        }
      } else if (warp == 15) {
#pragma unroll
        for (int i = B_FT; i < NBAR; i++) mbar_init(bars + 8 * i, i < B_EA ? 1 : i < B_T ? 2 : 4);
#pragma unroll
        for (int i = 0; i < 8; i++) mbar_expect_tx(bars + 8 * (B_Z + i), U / 2);
        asm volatile("fence.mbarrier_init.release.cluster;" ::: "memory");
        asm volatile("fence.proxy.async.shared::cta;" ::: "memory");
      }
    }
    __syncwarp();
    asm volatile("bar.arrive 0, 384;" ::: "memory");
    asm volatile("bar.arrive 4, 256;" ::: "memory");
    __syncwarp();
    asm volatile("barrier.cluster.arrive.relaxed.aligned;" ::: "memory");
    asm volatile("bar.sync 3, 128;" ::: "memory");
    if (warp == 15 && !helper) {
        mbar_wait(bars + 8 * B_FE, 0);
        const uint32_t tag = (ld_x1(&ws->epoch[blockIdx.x * 8]) + 1) & 1;
        const int c = lane >> 4, jj = 16 * blockIdx.x + (lane & 15), jm = (2048 - jj) & 2047;
        const unsigned short* pr = (const unsigned short*)w_r + 256 * c;
        const unsigned short* pi = (const unsigned short*)w_i + 256 * c;
        const float wr = 0.25f * (bf_lo(__ldg(pr + jj * 257)) + bf_lo(__ldg(pr + jm * 257)));
        const float wi = 0.25f * (bf_lo(__ldg(pi + jj * 257)) - bf_lo(__ldg(pi + jm * 257)));
        st_u2(ws->Wh + c * 2048 + jj, c ? pack_bf16(-wi, wr) : pack_bf16(wr, wi), tag);
        __syncwarp();
        hint_add_if(lane == 0, &ws->cntW[0]);
        mbar_wait(bars + 8 * B_XS, 0);
        const uint32_t t0 = (uint32_t)clock();
        uint4 v;
        do { v = ld_x4(ws->gate + rb * 128 + 4 * lane); spin_guard(t0); } while (__any_sync(0xffffffffu, ((v.x ^ tag) | (v.y ^ tag) | (v.z ^ tag) | (v.w ^ tag)) & 1));
        *(uint4*)(smem + OFF_G + lane * 16) = v;
        __syncwarp();
        mbar_arrive_if(lane < 4, bars + 8 * B_G);
      }
    auto part_load = [&](int i, unsigned ep1) {
      const uint32_t bytes = i < 2 ? U : U / 2;
      mbar_wait(bars + 8 * (B_PZ + (i == 0)), 0);
      mbar_expect_tx(bars + 8 * (B_HP + i), bytes);
      flag_wait(&ws->cntP[32 * (rb * 8 + j) + 8 * i], ep1 * (i < 2 ? 8u : 4u));
      bulk_load(sb + (i == 0 ? OFF_T : i == 1 ? 0 : i * (U / 2)), ws->part + (size_t)(rb * 8 + j) * 3072 + (i < 2 ? i * 1024 : 1024 + i * 512), bytes, bars + 8 * (B_HP + i));
      if (i == 2) PROF_EV(26);
    };
    if ((!helper || warp == 15) && elect_one()) {
      if (warp < 14) {
        const int p = warp - 12;
#pragma unroll 1
        for (int i = 4 + p; i < 14; i += 2) asm volatile("prefetch.tensormap [%0];" ::"l"((const char*)&maps + i * 128) : "memory");
#pragma unroll 1
        for (int n = 2; n < 31; n++) {
          const bool table = n == 4 || n >= 29;
          const bool half = n >= 17 && n < 21;
          const int q = n < 4 ? n : n < 17 ? n - 1 : n - 5;
          const CUtensorMap* m = table ? &maps.e : half ? &maps.g32 + p : &maps.g64 + p;
          const int c0 = table ? 0 : half ? f_half : f_full + 64 * (q >> 3);
          const int c1 = table ? (2 * rb + ((n & 1) ^ 1)) * 128 + 64 * p : half ? 128 * (n - 17) : 64 * (q & 7);
          const uint32_t fb = bars + 8 * (B_FA + (n & 3)), dst = sb + OFF_RING + (n & 3) * U + p * 8192;
          if (n < 4) mbar_wait(bars + 8 * (B_FE + n - 2), 0);
          else mbar_wait(bars + 8 * (B_EA + (n & 3)), ((n >> 2) & 1) ^ 1);
          tma2d(dst, m, fb, c0, c1);
          if (p == 0) mbar_expect_tx(fb, U);
        }
        part_load(2 + p, ld_x1(&ws->epoch[blockIdx.x * 8]) + 1);
      } else if (warp == 15) {
        const unsigned ep1 = ld_x1(&ws->epoch[blockIdx.x * 8]) + 1;
        flag_wait(&ws->cntX[helper ? 0 : 32 * j], ep1 * 16u);
        PROF_EV(22);
        mbar_expect_tx(bars + 8 * B_HX, U);
        bulk_load(sb + OFF_XB, ws->X + (size_t)(helper ? 128 : kg * 8 + tn) * 8192, U, bars + 8 * B_HX);
        if (!helper) {
          flag_wait(&ws->cntT[32 * q4], ep1 * 128u);
          PROF_EV(23);
          mbar_expect_tx(bars + 8 * B_TL, U);
          tma3d(sb + OFF_T, &maps.t, bars + 8 * B_TL, 64 * j, 0, 2 * rb);
          part_load(0, ep1); part_load(1, ep1);
          mbar_wait(bars + 8 * (B_HP + 2), 0); mbar_wait(bars + 8 * (B_HP + 3), 0);
          ws->epoch[blockIdx.x * 8] = ep1;
        }
      } else {
#pragma unroll 1
        for (int q = 4; q < 8; q++) xf_load(q);
        mbar_wait(bars + 8 * (B_FE + 2), 0);
        mbar_expect_tx(bars + 8 * B_E0, U);
        tma2d(sb + OFF_XB, &maps.e, bars + 8 * B_E0, 0, 2 * rb * 128);
        tma2d(sb + OFF_XB + 8192, &maps.e, bars + 8 * B_E0, 0, 2 * rb * 128 + 64);
#pragma unroll 1
        for (int h2 = 0; h2 < 2; h2++) {
          const int sg = 2 * rb + h2;
          mbar_wait(bars + 8 * (B_XS + h2), 0);
#pragma unroll 1
          for (int c = 0; c < 2; c++) {
            asm volatile("cp.async.bulk.tensor.4d.global.shared::cta.bulk_group [%0, {%2, %3, %4, %5}], [%1];" ::"l"(&maps.xs),
                         "r"(sb + OFF_XB + h2 * 8192 + c * 4096), "r"(0), "r"(sg), "r"(0), "r"(16 * j + 8 * c) : "memory");
            if (j == 0)
              asm volatile("cp.async.bulk.global.shared::cta.bulk_group [%0], [%1], 256;" ::"l"(ws->X + 128 * 8192 + c * 4096 + sg * 128),
                           "r"(sb + OFF_SP + h2 * 512 + c * 256) : "memory");
            if (SPACE && h2 + c < 2) __nanosleep(SPACE);
          }
        }
        bulk_done_signal(&ws->cntX[32 * j]);
        PROF_EV(20);
#pragma unroll 1
        for (int t = 0; t < 8; t++) {
          const int col = 64 * (((q4 + 1 + (t >> 1)) & 3) + 4 * ((t & 1) ? rank : 1 - rank));
          const uint32_t fb = bars + 8 * (B_FT + (t & 3)), dst = sb + (t & 3) * TB;
          mbar_wait(bars + 8 * (B_ET + (t < 3 ? t + 1 : t & 3)), t >> 2);
          mbar_expect_tx(fb, (t & 1) ? TB : 28672);
          if (t & 1) tma3d(dst + 28672, &maps.fg, fb, col, 16 * rank, 4 * q4);
          tma2d(dst, &maps.d224, fb, col, 224 * j);
        }
      }
    }
  }
}

typedef CUresult (*EncodeFn)(CUtensorMap*, CUtensorMapDataType, cuuint32_t, void*, const cuuint64_t*, const cuuint64_t*, const cuuint32_t*,
                             const cuuint32_t*, CUtensorMapInterleave, CUtensorMapSwizzle, CUtensorMapL2promotion, CUtensorMapFloatOOBfill);

static void encode(EncodeFn f, CUtensorMap* m, const void* base, int rank, const cuuint64_t* dims, const cuuint64_t* strides, const cuuint32_t* box,
                   CUtensorMapSwizzle sw) {
  cuuint32_t es[5] = {1, 1, 1, 1, 1};
  f(m, CU_TENSOR_MAP_DATA_TYPE_BFLOAT16, rank, (void*)base, dims, strides, box, es, CU_TENSOR_MAP_INTERLEAVE_NONE, sw,
    CU_TENSOR_MAP_L2_PROMOTION_L2_128B, CU_TENSOR_MAP_FLOAT_OOB_FILL_NONE);
}

extern "C" void kernel_launch(void* const* d_in, const int* in_sizes, int n_in, void* d_out, int out_size) {
  (void)in_sizes; (void)n_in; (void)out_size;
  const __nv_bfloat16* x = (const __nv_bfloat16*)d_in[0];
  const __nv_bfloat16* w_r = (const __nv_bfloat16*)d_in[1];
  const __nv_bfloat16* w_i = (const __nv_bfloat16*)d_in[2];
  const __nv_bfloat16* Wg = (const __nv_bfloat16*)d_in[4];
  const __nv_bfloat16* Wu = (const __nv_bfloat16*)d_in[5];
  const __nv_bfloat16* Wd = (const __nv_bfloat16*)d_in[6];
  const __nv_bfloat16* gw = (const __nv_bfloat16*)d_in[7];

  void* fp = nullptr; cudaDriverEntryPointQueryResult qr;
  cudaGetDriverEntryPoint("cuTensorMapEncodeTiled", &fp, cudaEnableDefault, &qr);
  EncodeFn enc = (EncodeFn)fp;
  void *pFT, *pET, *pDT, *pW;
  cudaGetSymbolAddress(&pDT, g_DT); cudaGetSymbolAddress(&pW, g_work);
  void *pX = ((Work*)pW)->X, *pT = ((Work*)pW)->T;
  cudaGetSymbolAddress(&pFT, g_FT); cudaGetSymbolAddress(&pET, g_ET);

  Maps mp;
  const CUtensorMapSwizzle S128 = CU_TENSOR_MAP_SWIZZLE_128B, S64 = CU_TENSOR_MAP_SWIZZLE_64B;
  { cuuint64_t d[3] = {512, 64, 32}, s[2] = {32768, 1024}; cuuint32_t b[3] = {64, 64, 2}; encode(enc, &mp.x, x, 3, d, s, b, S128); }
  { cuuint64_t d[2] = {512, 512}, s[1] = {1024}; cuuint32_t b[2] = {64, 64}; encode(enc, &mp.ft, pFT, 2, d, s, b, S128); }
  { cuuint64_t d[4] = {128, 32, 2, 129}, s[3] = {256, 8192, 16384}; cuuint32_t b[4] = {128, 1, 2, 8}; encode(enc, &mp.xs, pX, 4, d, s, b, CU_TENSOR_MAP_SWIZZLE_NONE); }
  { cuuint64_t d[4] = {64, 32, 64, 8}, s[3] = {65536, 1024, 128}; cuuint32_t b[4] = {16, 32, 2, 2}; encode(enc, &mp.ts, pT, 4, d, s, b, CU_TENSOR_MAP_SWIZZLE_NONE); }
  { cuuint64_t d[3] = {512, 32, 16}, s[2] = {1024, 32768}; cuuint32_t b[3] = {64, 16, 4}; encode(enc, &mp.fg, pFT, 3, d, s, b, S128); }
  { cuuint64_t d[3] = {512, 64, 32}, s[2] = {1024, 65536}; cuuint32_t b[3] = {64, 64, 2}; encode(enc, &mp.t, pT, 3, d, s, b, S128); }
  { cuuint64_t d[2] = {64, 4096}, s[1] = {128}; cuuint32_t b[2] = {64, 64}; encode(enc, &mp.e, pET, 2, d, s, b, S128); }
  { cuuint64_t d[2] = {1792, 512}, s[1] = {3584}; cuuint32_t b[2] = {64, 64}, b2[2] = {32, 128};
    encode(enc, &mp.g64, Wg, 2, d, s, b, S128); encode(enc, &mp.u64, Wu, 2, d, s, b, S128);
    encode(enc, &mp.g32, Wg, 2, d, s, b2, S64); encode(enc, &mp.u32, Wu, 2, d, s, b2, S64); }
  { cuuint64_t d[2] = {512, 1792}, s[1] = {1024}; cuuint32_t b[2] = {64, 224}; encode(enc, &mp.d224, Wd, 2, d, s, b, S128); }
  { cuuint64_t d[4] = {264, 32, 8, 8}, s[3] = {32896, 512, 4112}; cuuint32_t b[4] = {24, 32, 2, 1};
    encode(enc, &mp.wr, w_r, 4, d, s, b, CU_TENSOR_MAP_SWIZZLE_NONE); encode(enc, &mp.wi, w_i, 4, d, s, b, CU_TENSOR_MAP_SWIZZLE_NONE); }

  cudaFuncSetAttribute(fused_kernel, cudaFuncAttributeMaxDynamicSharedMemorySize, SMEM_BYTES);
  fused_kernel<<<NCTA, 512, SMEM_BYTES>>>((Work*)pW, (const uint16_t*)pDT, w_r, w_i, gw, x, (__nv_bfloat16*)d_out, mp);
}
```

```cpp
#include <cuda_runtime.h>
#include <cuda_bf16.h>
#include <cuda.h>
#include <stdint.h>

namespace tbl {
constexpr double PI = 3.14159265358979323846264338327950288;
constexpr double sin_s(double x) { double t = x, s = x; for (int n = 1; n < 12; n++) { t *= -x * x / ((2 * n) * (2 * n + 1)); s += t; } return s; }
constexpr double cos_s(double x) { double t = 1, s = 1; for (int n = 1; n < 12; n++) { t *= -x * x / ((2 * n - 1) * (2 * n)); s += t; } return s; }
constexpr double cos2048(int m) {
  m &= 2047; if (m > 1024) m = 2048 - m;
  bool neg = false; if (m > 512) { m = 1024 - m; neg = true; }
  double v = (m <= 256) ? cos_s(2 * PI * m / 2048) : sin_s(2 * PI * (512 - m) / 2048);
  return neg ? -v : v;
}
constexpr uint16_t to_bf16(double v) {
  if (v == 0) return 0;
  uint16_t s = 0; if (v < 0) { s = 0x8000; v = -v; }
  int e = 0; while (v >= 2) { v /= 2; e++; } while (v < 1) { v *= 2; e--; }
  double m = (v - 1) * 128; int mi = (int)m; double fr = m - mi;
  if (fr > 0.5 || (fr == 0.5 && (mi & 1))) mi++;
  if (mi == 128) { mi = 0; e++; }
  return (uint16_t)(s | ((e + 127) << 7) | mi);
}
struct CosT { uint16_t v[2048]; constexpr CosT() : v() { for (int i = 0; i < 2048; i++) v[i] = to_bf16(cos2048(i)); } };
struct alignas(1024) FT {
  uint16_t v[512 * 512];
  constexpr FT() : v() {
    CosT c;
    for (int r = 0; r < 512; r++) {
      int k = (r >> 5) * 16 + 2 * (r & 7) + ((r >> 4) & 1), e = (r >> 3) & 1;
      int mul = 4 * k, add = e ? 512 : 0;
      if (k == 0 && e == 1) { mul = 1024; add = 0; }
      for (int d = 0; d < 512; d++) v[r * 512 + d] = c.v[(d * mul + add) & 2047];
    }
  }
};
struct alignas(1024) ET {
  uint16_t v[2048 * 128];
  constexpr ET() : v() {
    CosT c;
    for (int s = 0; s < 2048; s++)
      for (int j = 0; j < 64; j++) {
        const int o = (s & 31) * 8192 + (s >> 5) * 64 + j;
        v[o] = c.v[(s * j) & 2047]; v[o + 4096] = c.v[(s * j + 512) & 2047];
      }
  }
};
struct alignas(1024) DT {
  uint16_t v[64 * 64];
  constexpr DT() : v() {
    CosT c;
    for (int r = 0; r < 64; r++)
      for (int n = 0; n < 64; n++) {
        const int sg = r >> 1, s0 = (sg & ~6) | ((sg & 2) << 1) | ((sg & 4) >> 1), e = r & 1, f = n & 1;
        const int m = 64 * s0 * (n >> 1) + (e == f ? 0 : e ? -512 : 512);
        v[r * 64 + (((n >> 3) ^ (r & 7)) << 3) + (n & 7)] = c.v[m & 2047];
      }
  }
};
}

__device__ constexpr tbl::FT g_FT = tbl::FT();
__device__ constexpr tbl::ET g_ET = tbl::ET();
__device__ constexpr tbl::DT g_DT = tbl::DT();

struct alignas(1024) Work {
  unsigned epoch[132 * 8];
  unsigned cntX[8 * 32], cntT[8 * 32], cntP[128 * 32], cntW[32], cntH[32];
  alignas(16) float gate[16 * 128];
  alignas(16) uint2 Wh[2 * 2048];
  alignas(16) uint2 Ts[32 * 64];
  alignas(1024) uint16_t X[129 * 8192];
  alignas(1024) uint16_t T[32 * 64 * 512];
  alignas(1024) uint4 part[128 * 3 * 1024];
};
__device__ Work g_work;
#define PROF_EV(i) do {} while (0)
#define PROF_CK(i) do {} while (0)

__device__ __forceinline__ uint32_t smem_u32(const void* p) { return (uint32_t)__cvta_generic_to_shared(p); }
__device__ __forceinline__ void mbar_init(uint32_t bar, uint32_t cnt) { asm volatile("mbarrier.init.shared::cta.b64 [%0], %1;" ::"r"(bar), "r"(cnt)); }
__device__ __forceinline__ void mbar_expect_tx(uint32_t bar, uint32_t bytes) { asm volatile("mbarrier.arrive.expect_tx.shared::cta.b64 _, [%0], %1;" ::"r"(bar), "r"(bytes) : "memory"); }
__device__ __forceinline__ void mbar_arrive(uint32_t bar) { asm volatile("mbarrier.arrive.shared::cta.b64 _, [%0];" ::"r"(bar) : "memory"); }
__device__ __forceinline__ bool elect_one() {
  uint32_t p;
  asm volatile("{\n.reg .pred p;\nelect.sync _|p, 0xffffffff;\nselp.u32 %0, 1, 0, p;\n}" : "=r"(p));
  return p;
}
__device__ __forceinline__ void mbar_arrive_if(bool p, uint32_t bar) {
  asm volatile("{\n.reg .pred p;\nsetp.ne.b32 p, %1, 0;\n@p mbarrier.arrive.shared::cta.b64 _, [%0];\n}" ::"r"(bar), "r"((int)p) : "memory");
}
__device__ __forceinline__ void hint_add_if(bool p, unsigned* a) {
  asm volatile("{\n.reg .pred p;\nsetp.ne.b32 p, %1, 0;\n@p red.relaxed.gpu.global.add.u32 [%0], 1;\n}" ::"l"(a), "r"((int)p) : "memory");
}
__device__ __forceinline__ bool mbar_try(uint32_t bar, uint32_t parity) {
  uint32_t ok;
  asm volatile("{\n.reg .pred p;\nmbarrier.test_wait.parity.shared::cta.b64 p, [%1], %2;\nselp.u32 %0, 1, 0, p;\n}" : "=r"(ok) : "r"(bar), "r"(parity) : "memory");
  return ok;
}
__device__ __forceinline__ void mbar_wait(uint32_t bar, uint32_t parity) {
  asm volatile(
      "{\n.reg .pred p;\n.reg .u32 n;\nmov.u32 n, 0;\n"
      "W_LOOP:\nmbarrier.try_wait.parity.shared::cta.b64 p, [%0], %1;\n@p bra W_DONE;\n"
      "add.u32 n, n, 1;\nsetp.lt.u32 p, n, 0x40000;\n@p bra W_LOOP;\ntrap;\nW_DONE:\n}" ::"r"(bar), "r"(parity) : "memory");
}
__device__ __forceinline__ void bulk_load(uint32_t dst, const void* src, uint32_t bytes, uint32_t bar) {
  asm volatile("cp.async.bulk.shared::cluster.global.mbarrier::complete_tx::bytes [%0], [%1], %2, [%3];" ::"r"(dst), "l"(src), "r"(bytes), "r"(bar) : "memory");
}
__device__ __forceinline__ void spin_guard(uint32_t t0) { if ((uint32_t)clock() - t0 > (1u << 30)) __trap(); }
__device__ __forceinline__ float2 ld_x2(const float2* p) { float2 v; asm volatile("ld.relaxed.gpu.global.v2.f32 {%0,%1}, [%2];" : "=f"(v.x), "=f"(v.y) : "l"(p) : "memory"); return v; }
__device__ __forceinline__ void st_u2(uint2* p, uint32_t a, uint32_t b) { asm volatile("st.relaxed.gpu.global.v2.u32 [%0], {%1,%2};" ::"l"(p), "r"(a), "r"(b) : "memory"); }
__device__ __forceinline__ uint32_t ld_x1(const void* p) { uint32_t v; asm volatile("ld.relaxed.gpu.global.u32 %0, [%1];" : "=r"(v) : "l"(p) : "memory"); return v; }
__device__ __forceinline__ uint4 ld_x4(const void* p) { uint4 v; asm volatile("ld.relaxed.gpu.global.v4.u32 {%0,%1,%2,%3}, [%4];" : "=r"(v.x), "=r"(v.y), "=r"(v.z), "=r"(v.w) : "l"(p) : "memory"); return v; }
__device__ __forceinline__ uint32_t mapa(uint32_t a, uint32_t cta) { uint32_t r; asm volatile("mapa.shared::cluster.u32 %0, %1, %2;" : "=r"(r) : "r"(a), "r"(cta)); return r; }
__device__ __forceinline__ void stsm4t(uint32_t a, uint32_t r0, uint32_t r1, uint32_t r2, uint32_t r3) {
  asm volatile("stmatrix.sync.aligned.m8n8.x4.trans.shared.b16 [%0], {%1,%2,%3,%4};" ::"r"(a), "r"(r0), "r"(r1), "r"(r2), "r"(r3) : "memory");
}
__device__ __forceinline__ void hint_add(unsigned* p) { asm volatile("red.relaxed.gpu.global.add.u32 [%0], 1;" ::"l"(p) : "memory"); }
__device__ __forceinline__ void hint_wait(const unsigned* p, unsigned target) {
  const uint32_t t0 = (uint32_t)clock();
  while ((int)(ld_x1(p) - target) < 0) spin_guard(t0);
}
__device__ __forceinline__ void bulk_done_signal(unsigned* p) {
  asm volatile("cp.async.bulk.commit_group;\ncp.async.bulk.wait_group 0;\nfence.proxy.async.global;" ::: "memory");
  hint_add(p);
}
__device__ __forceinline__ void flag_wait(const unsigned* p, unsigned target) {
  hint_wait(p, target);
  asm volatile("fence.proxy.async.global;" ::: "memory");
}
__device__ __forceinline__ void tma2d(uint32_t dst, const CUtensorMap* m, uint32_t bar, int c0, int c1) {
  asm volatile("cp.async.bulk.tensor.2d.shared::cluster.global.mbarrier::complete_tx::bytes [%0], [%1, {%3, %4}], [%2];" ::"r"(dst), "l"(m), "r"(bar), "r"(c0), "r"(c1) : "memory");
}
__device__ __forceinline__ void tma3d(uint32_t dst, const CUtensorMap* m, uint32_t bar, int c0, int c1, int c2) {
  asm volatile("cp.async.bulk.tensor.3d.shared::cluster.global.mbarrier::complete_tx::bytes [%0], [%1, {%3, %4, %5}], [%2];" ::"r"(dst), "l"(m), "r"(bar), "r"(c0), "r"(c1), "r"(c2) : "memory");
}
__device__ __forceinline__ void tma4d(uint32_t dst, const CUtensorMap* m, uint32_t bar, int c0, int c1, int c2, int c3) {
  asm volatile("cp.async.bulk.tensor.4d.shared::cluster.global.mbarrier::complete_tx::bytes [%0], [%1, {%3, %4, %5, %6}], [%2];" ::"r"(dst), "l"(m), "r"(bar), "r"(c0), "r"(c1), "r"(c2), "r"(c3) : "memory");
}
__device__ __forceinline__ void wg_fence() { asm volatile("wgmma.fence.sync.aligned;" ::: "memory"); }
__device__ __forceinline__ void wg_commit() { asm volatile("wgmma.commit_group.sync.aligned;" ::: "memory"); }
template <int N> __device__ __forceinline__ void wg_wait() { asm volatile("wgmma.wait_group.sync.aligned %0;" ::"n"(N) : "memory"); }
template <int O, int N, int NN> __device__ __forceinline__ void fence_regs(float (&d)[NN]) {
#pragma unroll
  for (int i = 0; i < N; i++) asm volatile("" : "+f"(d[O + i])::"memory");
}
__device__ __forceinline__ uint32_t pack_bf16(float lo, float hi) {
  uint32_t r; asm("cvt.rn.bf16x2.f32 %0, %1, %2;" : "=r"(r) : "f"(hi), "f"(lo)); return r;
}
__device__ __forceinline__ uint32_t pack_pin(float lo, float hi) {
  uint32_t r; asm volatile("cvt.rn.bf16x2.f32 %0, %1, %2;" : "=r"(r) : "f"(hi), "f"(lo) : "memory"); return r;
}
__device__ __forceinline__ uint32_t add_bf2(uint32_t a, uint32_t b) { uint32_t r; asm("add.rn.bf16x2 %0, %1, %2;" : "=r"(r) : "r"(a), "r"(b)); return r; }
__device__ __forceinline__ float bf_lo(uint32_t u) { return __uint_as_float(u << 16); }
__device__ __forceinline__ float bf_hi(uint32_t u) { return __uint_as_float(u & 0xffff0000u); }

__device__ __forceinline__ uint64_t d128(uint32_t lo) { uint64_t d; asm("mov.b64 %0, {%1, 0x40000040};" : "=l"(d) : "r"(lo)); return d; }
__device__ __forceinline__ uint64_t d64(uint32_t lo) { uint64_t d; asm("mov.b64 %0, {%1, 0x80000020};" : "=l"(d) : "r"(lo)); return d; }
template<int O,int TB,int ACC,int NN> __device__ __forceinline__ void mma_ss64(float (&d)[NN], uint64_t da, uint64_t db, int sd = 0){
  if constexpr (ACC == 1) asm volatile("wgmma.mma_async.sync.aligned.m64n64k16.f32.bf16.bf16 {%0,%1,%2,%3,%4,%5,%6,%7,%8,%9,%10,%11,%12,%13,%14,%15,%16,%17,%18,%19,%20,%21,%22,%23,%24,%25,%26,%27,%28,%29,%30,%31}, %32, %33, 1, 1, 1, %35, %34;"
   : "+f"(d[O+0]), "+f"(d[O+1]), "+f"(d[O+2]), "+f"(d[O+3]), "+f"(d[O+4]), "+f"(d[O+5]), "+f"(d[O+6]), "+f"(d[O+7]), "+f"(d[O+8]), "+f"(d[O+9]), "+f"(d[O+10]), "+f"(d[O+11]), "+f"(d[O+12]), "+f"(d[O+13]), "+f"(d[O+14]), "+f"(d[O+15]), "+f"(d[O+16]), "+f"(d[O+17]), "+f"(d[O+18]), "+f"(d[O+19]), "+f"(d[O+20]), "+f"(d[O+21]), "+f"(d[O+22]), "+f"(d[O+23]), "+f"(d[O+24]), "+f"(d[O+25]), "+f"(d[O+26]), "+f"(d[O+27]), "+f"(d[O+28]), "+f"(d[O+29]), "+f"(d[O+30]), "+f"(d[O+31])
   : "l"(da), "l"(db), "n"(TB & 1), "n"(TB >> 1));
  else if constexpr (ACC == 0) asm volatile("wgmma.mma_async.sync.aligned.m64n64k16.f32.bf16.bf16 {%0,%1,%2,%3,%4,%5,%6,%7,%8,%9,%10,%11,%12,%13,%14,%15,%16,%17,%18,%19,%20,%21,%22,%23,%24,%25,%26,%27,%28,%29,%30,%31}, %32, %33, 0, 1, 1, %35, %34;"
   : "=f"(d[O+0]), "=f"(d[O+1]), "=f"(d[O+2]), "=f"(d[O+3]), "=f"(d[O+4]), "=f"(d[O+5]), "=f"(d[O+6]), "=f"(d[O+7]), "=f"(d[O+8]), "=f"(d[O+9]), "=f"(d[O+10]), "=f"(d[O+11]), "=f"(d[O+12]), "=f"(d[O+13]), "=f"(d[O+14]), "=f"(d[O+15]), "=f"(d[O+16]), "=f"(d[O+17]), "=f"(d[O+18]), "=f"(d[O+19]), "=f"(d[O+20]), "=f"(d[O+21]), "=f"(d[O+22]), "=f"(d[O+23]), "=f"(d[O+24]), "=f"(d[O+25]), "=f"(d[O+26]), "=f"(d[O+27]), "=f"(d[O+28]), "=f"(d[O+29]), "=f"(d[O+30]), "=f"(d[O+31])
   : "l"(da), "l"(db), "n"(TB & 1), "n"(TB >> 1));
  else asm volatile("{\n.reg .pred p;\nsetp.ne.b32 p, %36, 0;\nwgmma.mma_async.sync.aligned.m64n64k16.f32.bf16.bf16 {%0,%1,%2,%3,%4,%5,%6,%7,%8,%9,%10,%11,%12,%13,%14,%15,%16,%17,%18,%19,%20,%21,%22,%23,%24,%25,%26,%27,%28,%29,%30,%31}, %32, %33, p, 1, 1, %35, %34;\n}"
   : "+f"(d[O+0]), "+f"(d[O+1]), "+f"(d[O+2]), "+f"(d[O+3]), "+f"(d[O+4]), "+f"(d[O+5]), "+f"(d[O+6]), "+f"(d[O+7]), "+f"(d[O+8]), "+f"(d[O+9]), "+f"(d[O+10]), "+f"(d[O+11]), "+f"(d[O+12]), "+f"(d[O+13]), "+f"(d[O+14]), "+f"(d[O+15]), "+f"(d[O+16]), "+f"(d[O+17]), "+f"(d[O+18]), "+f"(d[O+19]), "+f"(d[O+20]), "+f"(d[O+21]), "+f"(d[O+22]), "+f"(d[O+23]), "+f"(d[O+24]), "+f"(d[O+25]), "+f"(d[O+26]), "+f"(d[O+27]), "+f"(d[O+28]), "+f"(d[O+29]), "+f"(d[O+30]), "+f"(d[O+31])
   : "l"(da), "l"(db), "n"(TB & 1), "n"(TB >> 1), "r"(sd));
}
template<int O,int TB,int ACC,int NN> __device__ __forceinline__ void mma_rs64(float (&d)[NN], uint32_t a0, uint32_t a1, uint32_t a2, uint32_t a3, uint64_t db, int sd = 0){
  if constexpr (ACC == 1) asm volatile("wgmma.mma_async.sync.aligned.m64n64k16.f32.bf16.bf16 {%0,%1,%2,%3,%4,%5,%6,%7,%8,%9,%10,%11,%12,%13,%14,%15,%16,%17,%18,%19,%20,%21,%22,%23,%24,%25,%26,%27,%28,%29,%30,%31}, {%32,%33,%34,%35}, %36, 1, 1, 1, %37;"
   : "+f"(d[O+0]), "+f"(d[O+1]), "+f"(d[O+2]), "+f"(d[O+3]), "+f"(d[O+4]), "+f"(d[O+5]), "+f"(d[O+6]), "+f"(d[O+7]), "+f"(d[O+8]), "+f"(d[O+9]), "+f"(d[O+10]), "+f"(d[O+11]), "+f"(d[O+12]), "+f"(d[O+13]), "+f"(d[O+14]), "+f"(d[O+15]), "+f"(d[O+16]), "+f"(d[O+17]), "+f"(d[O+18]), "+f"(d[O+19]), "+f"(d[O+20]), "+f"(d[O+21]), "+f"(d[O+22]), "+f"(d[O+23]), "+f"(d[O+24]), "+f"(d[O+25]), "+f"(d[O+26]), "+f"(d[O+27]), "+f"(d[O+28]), "+f"(d[O+29]), "+f"(d[O+30]), "+f"(d[O+31])
   : "r"(a0), "r"(a1), "r"(a2), "r"(a3), "l"(db), "n"(TB));
  else if constexpr (ACC == 0) asm volatile("wgmma.mma_async.sync.aligned.m64n64k16.f32.bf16.bf16 {%0,%1,%2,%3,%4,%5,%6,%7,%8,%9,%10,%11,%12,%13,%14,%15,%16,%17,%18,%19,%20,%21,%22,%23,%24,%25,%26,%27,%28,%29,%30,%31}, {%32,%33,%34,%35}, %36, 0, 1, 1, %37;"
   : "=f"(d[O+0]), "=f"(d[O+1]), "=f"(d[O+2]), "=f"(d[O+3]), "=f"(d[O+4]), "=f"(d[O+5]), "=f"(d[O+6]), "=f"(d[O+7]), "=f"(d[O+8]), "=f"(d[O+9]), "=f"(d[O+10]), "=f"(d[O+11]), "=f"(d[O+12]), "=f"(d[O+13]), "=f"(d[O+14]), "=f"(d[O+15]), "=f"(d[O+16]), "=f"(d[O+17]), "=f"(d[O+18]), "=f"(d[O+19]), "=f"(d[O+20]), "=f"(d[O+21]), "=f"(d[O+22]), "=f"(d[O+23]), "=f"(d[O+24]), "=f"(d[O+25]), "=f"(d[O+26]), "=f"(d[O+27]), "=f"(d[O+28]), "=f"(d[O+29]), "=f"(d[O+30]), "=f"(d[O+31])
   : "r"(a0), "r"(a1), "r"(a2), "r"(a3), "l"(db), "n"(TB));
  else asm volatile("{\n.reg .pred p;\nsetp.ne.b32 p, %38, 0;\nwgmma.mma_async.sync.aligned.m64n64k16.f32.bf16.bf16 {%0,%1,%2,%3,%4,%5,%6,%7,%8,%9,%10,%11,%12,%13,%14,%15,%16,%17,%18,%19,%20,%21,%22,%23,%24,%25,%26,%27,%28,%29,%30,%31}, {%32,%33,%34,%35}, %36, p, 1, 1, %37;\n}"
   : "+f"(d[O+0]), "+f"(d[O+1]), "+f"(d[O+2]), "+f"(d[O+3]), "+f"(d[O+4]), "+f"(d[O+5]), "+f"(d[O+6]), "+f"(d[O+7]), "+f"(d[O+8]), "+f"(d[O+9]), "+f"(d[O+10]), "+f"(d[O+11]), "+f"(d[O+12]), "+f"(d[O+13]), "+f"(d[O+14]), "+f"(d[O+15]), "+f"(d[O+16]), "+f"(d[O+17]), "+f"(d[O+18]), "+f"(d[O+19]), "+f"(d[O+20]), "+f"(d[O+21]), "+f"(d[O+22]), "+f"(d[O+23]), "+f"(d[O+24]), "+f"(d[O+25]), "+f"(d[O+26]), "+f"(d[O+27]), "+f"(d[O+28]), "+f"(d[O+29]), "+f"(d[O+30]), "+f"(d[O+31])
   : "r"(a0), "r"(a1), "r"(a2), "r"(a3), "l"(db), "n"(TB), "r"(sd));
}
template<int O,int TB,int ACC,int NN> __device__ __forceinline__ void mma_ss128(float (&d)[NN], uint64_t da, uint64_t db, int sd = 0){
  if constexpr (ACC == 1) asm volatile("wgmma.mma_async.sync.aligned.m64n128k16.f32.bf16.bf16 {%0,%1,%2,%3,%4,%5,%6,%7,%8,%9,%10,%11,%12,%13,%14,%15,%16,%17,%18,%19,%20,%21,%22,%23,%24,%25,%26,%27,%28,%29,%30,%31,%32,%33,%34,%35,%36,%37,%38,%39,%40,%41,%42,%43,%44,%45,%46,%47,%48,%49,%50,%51,%52,%53,%54,%55,%56,%57,%58,%59,%60,%61,%62,%63}, %64, %65, 1, 1, 1, %67, %66;"
   : "+f"(d[O+0]), "+f"(d[O+1]), "+f"(d[O+2]), "+f"(d[O+3]), "+f"(d[O+4]), "+f"(d[O+5]), "+f"(d[O+6]), "+f"(d[O+7]), "+f"(d[O+8]), "+f"(d[O+9]), "+f"(d[O+10]), "+f"(d[O+11]), "+f"(d[O+12]), "+f"(d[O+13]), "+f"(d[O+14]), "+f"(d[O+15]), "+f"(d[O+16]), "+f"(d[O+17]), "+f"(d[O+18]), "+f"(d[O+19]), "+f"(d[O+20]), "+f"(d[O+21]), "+f"(d[O+22]), "+f"(d[O+23]), "+f"(d[O+24]), "+f"(d[O+25]), "+f"(d[O+26]), "+f"(d[O+27]), "+f"(d[O+28]), "+f"(d[O+29]), "+f"(d[O+30]), "+f"(d[O+31]), "+f"(d[O+32]), "+f"(d[O+33]), "+f"(d[O+34]), "+f"(d[O+35]), "+f"(d[O+36]), "+f"(d[O+37]), "+f"(d[O+38]), "+f"(d[O+39]), "+f"(d[O+40]), "+f"(d[O+41]), "+f"(d[O+42]), "+f"(d[O+43]), "+f"(d[O+44]), "+f"(d[O+45]), "+f"(d[O+46]), "+f"(d[O+47]), "+f"(d[O+48]), "+f"(d[O+49]), "+f"(d[O+50]), "+f"(d[O+51]), "+f"(d[O+52]), "+f"(d[O+53]), "+f"(d[O+54]), "+f"(d[O+55]), "+f"(d[O+56]), "+f"(d[O+57]), "+f"(d[O+58]), "+f"(d[O+59]), "+f"(d[O+60]), "+f"(d[O+61]), "+f"(d[O+62]), "+f"(d[O+63])
   : "l"(da), "l"(db), "n"(TB & 1), "n"(TB >> 1));
  else if constexpr (ACC == 0) asm volatile("wgmma.mma_async.sync.aligned.m64n128k16.f32.bf16.bf16 {%0,%1,%2,%3,%4,%5,%6,%7,%8,%9,%10,%11,%12,%13,%14,%15,%16,%17,%18,%19,%20,%21,%22,%23,%24,%25,%26,%27,%28,%29,%30,%31,%32,%33,%34,%35,%36,%37,%38,%39,%40,%41,%42,%43,%44,%45,%46,%47,%48,%49,%50,%51,%52,%53,%54,%55,%56,%57,%58,%59,%60,%61,%62,%63}, %64, %65, 0, 1, 1, %67, %66;"
   : "=f"(d[O+0]), "=f"(d[O+1]), "=f"(d[O+2]), "=f"(d[O+3]), "=f"(d[O+4]), "=f"(d[O+5]), "=f"(d[O+6]), "=f"(d[O+7]), "=f"(d[O+8]), "=f"(d[O+9]), "=f"(d[O+10]), "=f"(d[O+11]), "=f"(d[O+12]), "=f"(d[O+13]), "=f"(d[O+14]), "=f"(d[O+15]), "=f"(d[O+16]), "=f"(d[O+17]), "=f"(d[O+18]), "=f"(d[O+19]), "=f"(d[O+20]), "=f"(d[O+21]), "=f"(d[O+22]), "=f"(d[O+23]), "=f"(d[O+24]), "=f"(d[O+25]), "=f"(d[O+26]), "=f"(d[O+27]), "=f"(d[O+28]), "=f"(d[O+29]), "=f"(d[O+30]), "=f"(d[O+31]), "=f"(d[O+32]), "=f"(d[O+33]), "=f"(d[O+34]), "=f"(d[O+35]), "=f"(d[O+36]), "=f"(d[O+37]), "=f"(d[O+38]), "=f"(d[O+39]), "=f"(d[O+40]), "=f"(d[O+41]), "=f"(d[O+42]), "=f"(d[O+43]), "=f"(d[O+44]), "=f"(d[O+45]), "=f"(d[O+46]), "=f"(d[O+47]), "=f"(d[O+48]), "=f"(d[O+49]), "=f"(d[O+50]), "=f"(d[O+51]), "=f"(d[O+52]), "=f"(d[O+53]), "=f"(d[O+54]), "=f"(d[O+55]), "=f"(d[O+56]), "=f"(d[O+57]), "=f"(d[O+58]), "=f"(d[O+59]), "=f"(d[O+60]), "=f"(d[O+61]), "=f"(d[O+62]), "=f"(d[O+63])
   : "l"(da), "l"(db), "n"(TB & 1), "n"(TB >> 1));
  else asm volatile("{\n.reg .pred p;\nsetp.ne.b32 p, %68, 0;\nwgmma.mma_async.sync.aligned.m64n128k16.f32.bf16.bf16 {%0,%1,%2,%3,%4,%5,%6,%7,%8,%9,%10,%11,%12,%13,%14,%15,%16,%17,%18,%19,%20,%21,%22,%23,%24,%25,%26,%27,%28,%29,%30,%31,%32,%33,%34,%35,%36,%37,%38,%39,%40,%41,%42,%43,%44,%45,%46,%47,%48,%49,%50,%51,%52,%53,%54,%55,%56,%57,%58,%59,%60,%61,%62,%63}, %64, %65, p, 1, 1, %67, %66;\n}"
   : "+f"(d[O+0]), "+f"(d[O+1]), "+f"(d[O+2]), "+f"(d[O+3]), "+f"(d[O+4]), "+f"(d[O+5]), "+f"(d[O+6]), "+f"(d[O+7]), "+f"(d[O+8]), "+f"(d[O+9]), "+f"(d[O+10]), "+f"(d[O+11]), "+f"(d[O+12]), "+f"(d[O+13]), "+f"(d[O+14]), "+f"(d[O+15]), "+f"(d[O+16]), "+f"(d[O+17]), "+f"(d[O+18]), "+f"(d[O+19]), "+f"(d[O+20]), "+f"(d[O+21]), "+f"(d[O+22]), "+f"(d[O+23]), "+f"(d[O+24]), "+f"(d[O+25]), "+f"(d[O+26]), "+f"(d[O+27]), "+f"(d[O+28]), "+f"(d[O+29]), "+f"(d[O+30]), "+f"(d[O+31]), "+f"(d[O+32]), "+f"(d[O+33]), "+f"(d[O+34]), "+f"(d[O+35]), "+f"(d[O+36]), "+f"(d[O+37]), "+f"(d[O+38]), "+f"(d[O+39]), "+f"(d[O+40]), "+f"(d[O+41]), "+f"(d[O+42]), "+f"(d[O+43]), "+f"(d[O+44]), "+f"(d[O+45]), "+f"(d[O+46]), "+f"(d[O+47]), "+f"(d[O+48]), "+f"(d[O+49]), "+f"(d[O+50]), "+f"(d[O+51]), "+f"(d[O+52]), "+f"(d[O+53]), "+f"(d[O+54]), "+f"(d[O+55]), "+f"(d[O+56]), "+f"(d[O+57]), "+f"(d[O+58]), "+f"(d[O+59]), "+f"(d[O+60]), "+f"(d[O+61]), "+f"(d[O+62]), "+f"(d[O+63])
   : "l"(da), "l"(db), "n"(TB & 1), "n"(TB >> 1), "r"(sd));
}
template<int O,int TB,int ACC,int NN> __device__ __forceinline__ void mma_rs128(float (&d)[NN], uint32_t a0, uint32_t a1, uint32_t a2, uint32_t a3, uint64_t db, int sd = 0){
  if constexpr (ACC == 1) asm volatile("wgmma.mma_async.sync.aligned.m64n128k16.f32.bf16.bf16 {%0,%1,%2,%3,%4,%5,%6,%7,%8,%9,%10,%11,%12,%13,%14,%15,%16,%17,%18,%19,%20,%21,%22,%23,%24,%25,%26,%27,%28,%29,%30,%31,%32,%33,%34,%35,%36,%37,%38,%39,%40,%41,%42,%43,%44,%45,%46,%47,%48,%49,%50,%51,%52,%53,%54,%55,%56,%57,%58,%59,%60,%61,%62,%63}, {%64,%65,%66,%67}, %68, 1, 1, 1, %69;"
   : "+f"(d[O+0]), "+f"(d[O+1]), "+f"(d[O+2]), "+f"(d[O+3]), "+f"(d[O+4]), "+f"(d[O+5]), "+f"(d[O+6]), "+f"(d[O+7]), "+f"(d[O+8]), "+f"(d[O+9]), "+f"(d[O+10]), "+f"(d[O+11]), "+f"(d[O+12]), "+f"(d[O+13]), "+f"(d[O+14]), "+f"(d[O+15]), "+f"(d[O+16]), "+f"(d[O+17]), "+f"(d[O+18]), "+f"(d[O+19]), "+f"(d[O+20]), "+f"(d[O+21]), "+f"(d[O+22]), "+f"(d[O+23]), "+f"(d[O+24]), "+f"(d[O+25]), "+f"(d[O+26]), "+f"(d[O+27]), "+f"(d[O+28]), "+f"(d[O+29]), "+f"(d[O+30]), "+f"(d[O+31]), "+f"(d[O+32]), "+f"(d[O+33]), "+f"(d[O+34]), "+f"(d[O+35]), "+f"(d[O+36]), "+f"(d[O+37]), "+f"(d[O+38]), "+f"(d[O+39]), "+f"(d[O+40]), "+f"(d[O+41]), "+f"(d[O+42]), "+f"(d[O+43]), "+f"(d[O+44]), "+f"(d[O+45]), "+f"(d[O+46]), "+f"(d[O+47]), "+f"(d[O+48]), "+f"(d[O+49]), "+f"(d[O+50]), "+f"(d[O+51]), "+f"(d[O+52]), "+f"(d[O+53]), "+f"(d[O+54]), "+f"(d[O+55]), "+f"(d[O+56]), "+f"(d[O+57]), "+f"(d[O+58]), "+f"(d[O+59]), "+f"(d[O+60]), "+f"(d[O+61]), "+f"(d[O+62]), "+f"(d[O+63])
   : "r"(a0), "r"(a1), "r"(a2), "r"(a3), "l"(db), "n"(TB));
  else if constexpr (ACC == 0) asm volatile("wgmma.mma_async.sync.aligned.m64n128k16.f32.bf16.bf16 {%0,%1,%2,%3,%4,%5,%6,%7,%8,%9,%10,%11,%12,%13,%14,%15,%16,%17,%18,%19,%20,%21,%22,%23,%24,%25,%26,%27,%28,%29,%30,%31,%32,%33,%34,%35,%36,%37,%38,%39,%40,%41,%42,%43,%44,%45,%46,%47,%48,%49,%50,%51,%52,%53,%54,%55,%56,%57,%58,%59,%60,%61,%62,%63}, {%64,%65,%66,%67}, %68, 0, 1, 1, %69;"
   : "=f"(d[O+0]), "=f"(d[O+1]), "=f"(d[O+2]), "=f"(d[O+3]), "=f"(d[O+4]), "=f"(d[O+5]), "=f"(d[O+6]), "=f"(d[O+7]), "=f"(d[O+8]), "=f"(d[O+9]), "=f"(d[O+10]), "=f"(d[O+11]), "=f"(d[O+12]), "=f"(d[O+13]), "=f"(d[O+14]), "=f"(d[O+15]), "=f"(d[O+16]), "=f"(d[O+17]), "=f"(d[O+18]), "=f"(d[O+19]), "=f"(d[O+20]), "=f"(d[O+21]), "=f"(d[O+22]), "=f"(d[O+23]), "=f"(d[O+24]), "=f"(d[O+25]), "=f"(d[O+26]), "=f"(d[O+27]), "=f"(d[O+28]), "=f"(d[O+29]), "=f"(d[O+30]), "=f"(d[O+31]), "=f"(d[O+32]), "=f"(d[O+33]), "=f"(d[O+34]), "=f"(d[O+35]), "=f"(d[O+36]), "=f"(d[O+37]), "=f"(d[O+38]), "=f"(d[O+39]), "=f"(d[O+40]), "=f"(d[O+41]), "=f"(d[O+42]), "=f"(d[O+43]), "=f"(d[O+44]), "=f"(d[O+45]), "=f"(d[O+46]), "=f"(d[O+47]), "=f"(d[O+48]), "=f"(d[O+49]), "=f"(d[O+50]), "=f"(d[O+51]), "=f"(d[O+52]), "=f"(d[O+53]), "=f"(d[O+54]), "=f"(d[O+55]), "=f"(d[O+56]), "=f"(d[O+57]), "=f"(d[O+58]), "=f"(d[O+59]), "=f"(d[O+60]), "=f"(d[O+61]), "=f"(d[O+62]), "=f"(d[O+63])
   : "r"(a0), "r"(a1), "r"(a2), "r"(a3), "l"(db), "n"(TB));
  else asm volatile("{\n.reg .pred p;\nsetp.ne.b32 p, %70, 0;\nwgmma.mma_async.sync.aligned.m64n128k16.f32.bf16.bf16 {%0,%1,%2,%3,%4,%5,%6,%7,%8,%9,%10,%11,%12,%13,%14,%15,%16,%17,%18,%19,%20,%21,%22,%23,%24,%25,%26,%27,%28,%29,%30,%31,%32,%33,%34,%35,%36,%37,%38,%39,%40,%41,%42,%43,%44,%45,%46,%47,%48,%49,%50,%51,%52,%53,%54,%55,%56,%57,%58,%59,%60,%61,%62,%63}, {%64,%65,%66,%67}, %68, p, 1, 1, %69;\n}"
   : "+f"(d[O+0]), "+f"(d[O+1]), "+f"(d[O+2]), "+f"(d[O+3]), "+f"(d[O+4]), "+f"(d[O+5]), "+f"(d[O+6]), "+f"(d[O+7]), "+f"(d[O+8]), "+f"(d[O+9]), "+f"(d[O+10]), "+f"(d[O+11]), "+f"(d[O+12]), "+f"(d[O+13]), "+f"(d[O+14]), "+f"(d[O+15]), "+f"(d[O+16]), "+f"(d[O+17]), "+f"(d[O+18]), "+f"(d[O+19]), "+f"(d[O+20]), "+f"(d[O+21]), "+f"(d[O+22]), "+f"(d[O+23]), "+f"(d[O+24]), "+f"(d[O+25]), "+f"(d[O+26]), "+f"(d[O+27]), "+f"(d[O+28]), "+f"(d[O+29]), "+f"(d[O+30]), "+f"(d[O+31]), "+f"(d[O+32]), "+f"(d[O+33]), "+f"(d[O+34]), "+f"(d[O+35]), "+f"(d[O+36]), "+f"(d[O+37]), "+f"(d[O+38]), "+f"(d[O+39]), "+f"(d[O+40]), "+f"(d[O+41]), "+f"(d[O+42]), "+f"(d[O+43]), "+f"(d[O+44]), "+f"(d[O+45]), "+f"(d[O+46]), "+f"(d[O+47]), "+f"(d[O+48]), "+f"(d[O+49]), "+f"(d[O+50]), "+f"(d[O+51]), "+f"(d[O+52]), "+f"(d[O+53]), "+f"(d[O+54]), "+f"(d[O+55]), "+f"(d[O+56]), "+f"(d[O+57]), "+f"(d[O+58]), "+f"(d[O+59]), "+f"(d[O+60]), "+f"(d[O+61]), "+f"(d[O+62]), "+f"(d[O+63])
   : "r"(a0), "r"(a1), "r"(a2), "r"(a3), "l"(db), "n"(TB), "r"(sd));
}

#define NEARLY 0
#define XAHEAD 3
#define HEADN 6
#define WBATCH 1
#define WB 8
#define WSLEEP 20
#define XSPREAD 4
#define NOSEND 0
#define MSPLIT 2
#define PFALL 1
#define L2PF 0
#define STAG 1
#define EPF 2
#define XNB 2
#define FNB 0
#define GNB 0
#define TH 4
#define PF0 4
#define FSPLIT 1
#define MGLU 1
#define SPC 2
#define TL 14
#define GKB 4
#define T0A 8
#define TGATE 1
#define ZLATE 0
#define EARLYADD 0
#define OA 2
#define OB 11
#define EB 9
#define SPACE 100
#define WPF 1
#define WAFTER 7
#define WPACE 0
#define GATE_AT 4
#define TPACE 40
#define PFMODE 0
#define MAPMODE 1
template <int V> struct IC { static constexpr int value = V; };
struct Maps { CUtensorMap x, ft, g64, u64, e, wr, wi, xs, ts, t, g32, u32, d224, fg; };

constexpr int NCTA = 130;
constexpr int U = 16384;
constexpr int TB = 36864;
constexpr int OFF_RING = 8 * U, OFF_Z = 12 * U, OFF_XB = 12 * U, OFF_T = 13 * U, OFF_D = OFF_T;
constexpr int OFF_BAR = 14 * U, OFF_SP = OFF_BAR + 512, OFF_G = OFF_SP + 1024 + 128;
constexpr int SMEM_BYTES = OFF_G + 512;
constexpr int B_FX = 0, B_FA = 8, B_FT = 12, B_Z = 16, B_W = 24, B_HX = 25, B_TL = 26, B_HP = 27, B_WR = 31, B_E0 = 35;
constexpr int B_EA = 36, B_ET = 40, B_PZ = 44, B_RDY = 46, B_FE = 47;
constexpr int B_T = 51, B_XS = 52, B_G = 54, B_RD0 = 55, NBAR = 56;
__host__ __device__ constexpr int rslot(int n) { return n & 3; }
__host__ __device__ constexpr int rpar(int n) { return (n >> 2) & 1; }

__global__ void __cluster_dims__(2, 1, 1) __launch_bounds__(512, 1)
fused_kernel(Work* __restrict__ ws, const uint16_t* __restrict__ dtab, const __nv_bfloat16* __restrict__ w_r, const __nv_bfloat16* __restrict__ w_i,
             const __nv_bfloat16* __restrict__ gate_w, const __nv_bfloat16* __restrict__ x, __nv_bfloat16* __restrict__ out,
             const __grid_constant__ Maps maps) {
  extern __shared__ __align__(1024) uint8_t smem[];
  if (threadIdx.x < 32 && elect_one()) {
#pragma unroll
    for (int i = 0; i < PF0; i++) asm volatile("prefetch.tensormap [%0];" ::"l"((const char*)&maps + i * 128) : "memory");
  }
  const uint32_t sb = smem_u32(smem);
  const uint32_t bars = sb + OFF_BAR;
  const int tid = threadIdx.x, lane = tid & 31;
  const int warp = __shfl_sync(0xffffffffu, tid >> 5, 0);
  const bool helper = blockIdx.x >= 128;
  const int cl = (blockIdx.x >> 1) & 63, rank = blockIdx.x & 1;
  const int q4 = (cl & 1) | ((cl >> 2) & 2), rb = ((cl >> 1) & 3) | ((cl >> 4) << 2);
  const int j = 2 * q4 + rank;
  const int f_full = 448 * q4 + (rank ? 256 : 0);
  const int f_half = 448 * q4 + (rank ? 224 : 192);

  if (tid == 64) { PROF_EV(0); PROF_CK(40); }
  if (warp < 8) {
    if (!helper && tid < 32) {
      const int r = 16 * j + (tid & 15);
      asm volatile("prefetch.global.L2 [%0];" ::"l"(x + (size_t)(2 * rb + (r >> 6) + 32 * (r & 63)) * 512 + 64 * (tid >> 4)));
    }
    asm volatile("barrier.cluster.arrive.relaxed.aligned;" ::: "memory");
    asm volatile("setmaxnreg.inc.sync.aligned.u32 192;");
    if (!helper) {
      const int wg = warp >> 2, w = warp & 3, g = lane >> 2;
      const bool elect = (tid & 127) == 0;
      float cX[32], cA[64], cB[64], cC[64], ci[64], ct[64];
      const int zero = blockIdx.x >> 16;
      uint32_t h[56], yf[16];
      const uint32_t d0 = (sb & 0x3FFFF) >> 4;
      const uint32_t dK = d0 | (1u << 16), dN = d0 | (512u << 16);
      const uint32_t dX = dK + wg * 512;
      constexpr uint32_t RING = OFF_RING >> 4;
      auto waitA = [&](int n) { mbar_wait(bars + 8 * (B_FA + rslot(n)), rpar(n)); };
      auto freeA = [&](int n) { mbar_arrive_if(elect, bars + 8 * (B_EA + rslot(n))); };
      auto nop = [] {};

      asm volatile("bar.sync 0, 384;" ::: "memory");
#pragma unroll 1
      for (int i = 0; i < 4; i++) {
        const uint64_t dx = d128(dX + i * 2048), df = d128(dK + (OFF_XB >> 4) + (i & 1) * 1024);
        mbar_wait(bars + 8 * (B_FX + 2 * i), 0);
        wg_fence();
        mma_ss64<0, 0, 2>(cX, df, dx, i);
        mma_ss64<0, 0, 1>(cX, df + 2, dx + 2);
        wg_commit(); wg_wait<1>();
        mbar_arrive_if(elect && i, bars + 8 * (B_EA + rslot(i - 1)));
        mma_ss64<0, 0, 1>(cX, df + 4, dx + 4);
        mma_ss64<0, 0, 1>(cX, df + 6, dx + 6);
        if (i == 0 && tid == 0) PROF_EV(1);
        mbar_wait(bars + 8 * (B_FX + 2 * i + 1), 0);
        wg_fence();
#pragma unroll
        for (int k = 0; k < 4; k++) mma_ss64<0, 0, 1>(cX, df + (512 + k * 2), dx + (1024 + k * 2));
        wg_commit();
        waitA(i);
        wg_fence();
        const uint64_t da = d128(dX + i * 1024), db = d128(dN + RING + i * 1024);
        mma_ss128<0, 1, 2>(cA, da, db, i);
        wg_commit(); wg_wait<1>();
        mbar_arrive_if(elect, bars + 8 * (B_FE + i));
#pragma unroll
        for (int k = 1; k < 4; k++) mma_ss128<0, 1, 1>(cA, da + k * 2, db + k * 128);
        wg_commit();
      }
      fence_regs<0, 32>(cX);
#pragma unroll
      for (int e = 0; e < 16; e++) yf[e] = pack_pin(cX[2 * e], cX[2 * e + 1]);
      if (tid == 0) { PROF_EV(2); PROF_CK(42); }
      {
        waitA(4); mbar_wait(bars + 8 * B_E0, 0);
        const uint64_t de = d128(dN + (wg ? RING : OFF_XB >> 4));
        wg_fence();
        mma_rs128<0, 1, 0>(cB, yf[0], yf[1], yf[2], yf[3], de);
        wg_commit();
        wg_wait<1>();
        freeA(3);
#pragma unroll
        for (int k = 1; k < 4; k++) mma_rs128<0, 1, 1>(cB, yf[4 * k], yf[4 * k + 1], yf[4 * k + 2], yf[4 * k + 3], de + k * 128);
        wg_commit();
      }
      bool rel = false;
      auto acquire = [&](int n) {
        rel = elect;
        if (!mbar_try(bars + 8 * (B_FA + rslot(n)), rpar(n))) { wg_wait<0>(); freeA(n - 1); rel = false; waitA(n); }
      };
      auto freeP = [&](int n) { mbar_arrive_if(rel, bars + 8 * (B_EA + rslot(n - 1))); };
      auto ffn_step = [&](auto first, auto split, float (&acc)[64], int n, int kb, auto done, auto work) {
        constexpr int SPLIT = decltype(split)::value;
        acquire(n);
        wg_fence();
        const uint64_t dx = d128(dX + kb * 1024), db = d128(dN + RING + rslot(n) * 1024);
        mma_ss128<0, 1, decltype(first)::value>(acc, dx, db, kb);
#pragma unroll
        for (int k = 1; k < SPLIT; k++) mma_ss128<0, 1, 1>(acc, dx + k * 2, db + k * 128);
        wg_commit();
        work();
        wg_wait<1>();
        freeP(n);
        done();
        if (SPLIT < 4) {
          wg_fence();
#pragma unroll
          for (int k = SPLIT; k < 4; k++) mma_ss128<0, 1, 1>(acc, dx + k * 2, db + k * 128);
          wg_commit();
        }
      };
      {
        const int s0 = 2 * rb + wg, kr = 2 * ((s0 & 1) | ((s0 & 4) >> 1));
        const int m = lane >> 3, r = lane & 7;
        const uint32_t a0 = sb + OFF_XB + wg * 8192 + ((2 * (m >> 1) + (r >> 2)) * 2 + (w & 1)) * 256 + (m & 1) * 128 + (((2 * (r & 3) + ((w >> 1) ^ (r >> 2))) ^ (kr + (m & 1))) << 4);
        ffn_step(IC<1>(), IC<4>(), cA, 5, 4, [&] { fence_regs<0, 64>(cB); }, nop);
        asm volatile("bar.sync 5, 256;" ::: "memory");
        auto stage = [&](int i) {
          stsm4t(a0 + i * 2048, pack_bf16(cB[8 * i] - cB[34 + 8 * i], cB[8 * i + 1] - cB[35 + 8 * i]),
                 pack_bf16(cB[32 + 8 * i] + cB[8 * i + 2], cB[33 + 8 * i] + cB[8 * i + 3]),
                 pack_bf16(cB[8 * i + 4] - cB[38 + 8 * i], cB[8 * i + 5] - cB[39 + 8 * i]),
                 pack_bf16(cB[36 + 8 * i] + cB[8 * i + 6], cB[37 + 8 * i] + cB[8 * i + 7]));
          if (j == 0 && w == 0) {
            const uint32_t a1 = r ? sb + OFF_SP + 1024 : sb + OFF_SP + wg * 512 + (m & 1) * 256 + (m >> 1) * 128;
#pragma unroll
            for (int n = 2 * i; n < 2 * i + 2; n++)
              asm volatile("stmatrix.sync.aligned.m8n8.x4.shared.b16 [%0], {%1,%2,%3,%4};" ::"r"(a1 + ((n ^ (kr + (m >> 1)) ^ r) << 4)),
                           "r"(pack_bf16(cB[4 * n], cB[4 * n + 1])), "r"(pack_bf16(cB[4 * n + 2], cB[4 * n + 3])),
                           "r"(pack_bf16(cB[32 + 4 * n], cB[33 + 4 * n])), "r"(pack_bf16(cB[34 + 4 * n], cB[35 + 4 * n])) : "memory");
          }
        };
        auto publish = [&] {
          asm volatile("fence.proxy.async.shared::cta;" ::: "memory");
          __syncwarp();
          mbar_arrive_if(lane == 0, bars + 8 * (B_XS + wg));
          if (tid == 0) PROF_EV(3);
        };
        stage(0);
        ffn_step(IC<1>(), IC<FSPLIT>(), cA, 6, 5, nop, nop);
        stage(1);
        ffn_step(IC<1>(), IC<FSPLIT>(), cA, 7, 6, nop, nop);
        stage(2);
        ffn_step(IC<1>(), IC<2>(), cA, 8, 7, [&] { stage(3); }, nop);
        publish();
      }
      uint32_t gb0 = 0, gb1 = 0;
      uint32_t ob[2] = {0, 0};
      auto glu = [&](auto& acc, int half, int ho, int i0, int i1) {
#pragma unroll
        for (int i = i0; i < i1; i++)
          asm volatile("{\n.reg .b32 a, b;\ncvt.rn.relu.bf16x2.f32 a, %2, %1;\ncvt.rn.bf16x2.f32 b, %4, %3;\nmul.rn.bf16x2 a, a, b;\nmul.rn.bf16x2 %0, a, %5;\n}"
                       : "=r"(h[ho + i]) : "f"(acc[2 * i]), "f"(acc[2 * i + 1]), "f"(acc[half + 2 * i]), "f"(acc[half + 1 + 2 * i]), "r"(ob[i & 1]) : "memory");
      };
      ffn_step(IC<2>(), IC<1>(), cB, 9, zero, nop, nop);
#pragma unroll 1
      for (int kb = 1; kb < 8; kb++)
        ffn_step(IC<1>(), IC<FSPLIT>(), cB, 9 + kb, kb, nop, [&] {
          if (kb == GKB) {
            mbar_wait(bars + 8 * B_G, 0);
            asm volatile("ld.shared.u32 %0, [%2];\nld.shared.u32 %1, [%2+32];" : "=r"(gb0), "=r"(gb1) : "r"(sb + OFF_G + (wg * 64 + w * 16 + g) * 4) : "memory");
          } else if (kb == 5 + 2 * wg) {
            ob[0] = pack_bf16(1.0f - bf_hi(gb0), 1.0f - bf_hi(gb0)); ob[1] = pack_bf16(1.0f - bf_hi(gb1), 1.0f - bf_hi(gb1));
            glu(cA, 32, 0, 0, 16);
          }
        });
      const uint32_t tag = gb0 & 1;
      const float g0 = bf_hi(gb0), g1 = bf_hi(gb1);
      if (tid == 0) { PROF_EV(4); PROF_CK(43); }
      auto m_step = [&](auto first, int i) {
        acquire(17 + i);
        wg_fence();
        const uint64_t dx = d128(dX + i * 2048), dm = d64(dN + RING + rslot(17 + i) * 1024);
        mma_ss64<0, 1, decltype(first)::value>(ct, dx, dm);
#pragma unroll
        for (int k = 1; k < MSPLIT; k++) mma_ss64<0, 1, 1>(ct, dx + ((k >> 2) * 1024 + (k & 3) * 2), dm + k * 64);
        wg_commit();
        wg_wait<1>();
        freeP(17 + i);
        wg_fence();
#pragma unroll
        for (int k = MSPLIT; k < 8; k++) mma_ss64<0, 1, 1>(ct, dx + ((k >> 2) * 1024 + (k & 3) * 2), dm + k * 64);
        wg_commit();
      };
      m_step(IC<0>(), 0);
#pragma unroll 1
      for (int i = 1; i < 5; i++) {
        if (i == 1 + 2 * wg) glu(cB, 32, 16, 0, 16);
        if (i < 4) m_step(IC<1>(), i);
      }
      if (tid == 0) { PROF_EV(5); PROF_CK(44); }
      ffn_step(IC<0>(), IC<1>(), cC, 21, 0, nop, nop);
#pragma unroll 1
      for (int kb = 1; kb < 8; kb++)
        ffn_step(IC<1>(), IC<FSPLIT>(), cC, 21 + kb, kb, [&] { mbar_arrive_if(elect && !(kb & 1), bars + 8 * (B_ET + (kb >> 1) - 1)); }, [&] {
          if (kb == 1 + wg) glu(ct, 16, 48, 0, 8);
        });

      auto twait = [&](uint32_t bar, uint32_t par, int) { mbar_wait(bar, par); };
      const int fo = warp * 128 + lane;
      auto fetch = [&](uint4 (&pv)[4], int z) {
        twait(bars + 8 * (z < 4 ? B_Z + 2 * z + wg : z < 6 ? B_HP + z - 4 : B_HP + 2 + wg), 0, 8 + z);
        const uint8_t* src = smem + (z < 4 ? OFF_Z - z * U : z == 4 ? OFF_T : (z - 5) * U) + fo * 16;
#pragma unroll
        for (int i = 0; i < 4; i++) pv[i] = *(const uint4*)(src + i * 512);
      };
      const uint32_t peerZ = mapa(sb + OFF_Z + fo * 16, rank ^ 1), peerB = mapa(bars + 8 * (B_Z + wg), rank ^ 1);
      auto tile_mma = [&](auto off, int t, int k0, int k1) {
        constexpr int O = decltype(off)::value;
        const uint64_t db = d128(dN + (t & 3) * (TB >> 4)), dw = db + rank * 256, dm = db + (rank ? 0 : 1536);
#pragma unroll
        for (int k = k0; k < k1; k++) {
          if (k == 0 && O == 0) mma_rs64<O, 1, 2>(ct, h[0], h[1], h[2], h[3], dw, zero);
          else if (k < 14) mma_rs64<O, 1, 1>(ct, h[4 * k], h[4 * k + 1], h[4 * k + 2], h[4 * k + 3], k < 12 ? dw + k * 128 : dm + (k - 12) * 128);
          else if (k == 14) mma_rs64<O, 1, 2>(ct, yf[0], yf[1], yf[2], yf[3], db + k * 128, zero);
          else mma_rs64<O, 1, 1>(ct, yf[4 * k - 56], yf[4 * k - 55], yf[4 * k - 54], yf[4 * k - 53], db + k * 128);
        }
      };
      uint4 pv[4];
      const float sgn = rank ? -1.0f : 1.0f;
      auto odd_head = [&](int t) {
        twait(bars + 8 * (B_FT + (t & 3)), t >> 2, t);
        wg_fence();
        tile_mma(IC<32>(), t, 14, 18);
        wg_commit();
        if (t < 4) twait(bars + 8 * (t == 1 ? B_RD0 : B_RDY), 0, 14 + t);
        wg_wait<0>();
        mbar_arrive_if(elect && t < 6, bars + 8 * (B_ET + t - 1));
        fence_regs<0, 64>(ct);
#pragma unroll
        for (int i = 0; i < 4; i++) {
          uint32_t u[4];
#pragma unroll
          for (int e = 0; e < 4; e++) u[e] = pack_pin(fmaf(sgn, ct[32 + 8 * i + 2 * e], ct[8 * i + 2 * e]), fmaf(sgn, ct[33 + 8 * i + 2 * e], ct[8 * i + 2 * e + 1]));
          pv[i] = make_uint4(u[0], u[1], u[2], u[3]);
        }
        wg_fence();
        tile_mma(IC<32>(), t, 0, OA);
#pragma unroll
        for (int i = 0; i < 4; i++) {
          asm volatile("st.async.weak.shared::cluster.mbarrier::complete_tx::bytes.v4.b32 [%0], {%2,%3,%4,%5}, [%1];" ::"r"(peerZ - (t >> 1) * U + i * 512),
                       "r"(peerB + 16 * (t >> 1)), "r"(pv[i].x), "r"(pv[i].y), "r"(pv[i].z), "r"(pv[i].w) : "memory");
          tile_mma(IC<32>(), t, OA + i, OA + i + 1);
        }
        wg_commit();
      };
      asm volatile("barrier.cluster.wait.aligned;" ::: "memory");
      twait(bars + 8 * B_FT, 0, 0);
      if (wg) asm volatile("bar.sync 6, 256;" ::: "memory");
      wg_fence();
      tile_mma(IC<0>(), 0, 0, T0A);
      wg_commit();
      if (!wg) asm volatile("bar.arrive 6, 256;" ::: "memory");
      waitA(29 + wg);
      wg_wait<1>();
      mbar_arrive_if(elect, bars + 8 * (B_ET + 3));
      glu(cC, 32, 32, 0, 16);
      if (tid == 0) PROF_EV(6);
      if (tid == 128) PROF_EV(27);
      mbar_wait(bars + 8 * (j == 0 ? B_T : B_TL), 0);
      if (tid == 0) { PROF_EV(7); PROF_CK(45); }
      wg_fence();
      {
        const uint64_t dt = d128(dN + (OFF_T >> 4) + wg * 512), de = d128(dK + RING + (1 + wg) * 1024);
        mma_ss64<0, 1, 0>(ci, de, dt);
        mma_ss64<32, 1, 0>(ci, de + 512, dt);
#pragma unroll
        for (int k = 1; k < 4; k++) {
          mma_ss64<0, 1, 1>(ci, de + k * 2, dt + k * 128);
          mma_ss64<32, 1, 1>(ci, de + (512 + k * 2), dt + k * 128);
        }
        wg_commit();
      }
      tile_mma(IC<0>(), 0, T0A, 14);
      wg_commit();
      wg_wait<1>();
      if (elect) asm volatile("mbarrier.arrive.shared::cluster.b64 _, [%0];" ::"r"(mapa(bars + 8 * B_RDY, rank ^ 1)) : "memory");
      mbar_arrive_if(elect, bars + 8 * (B_PZ + 1));
      fence_regs<0, 64>(ci);
#pragma unroll
      for (int i = 0; i < 16; i++) {
        const float gg = ((i & 1) ? g1 : g0) * (2.0f / (2048.0f * 512.0f));
        if (i & 2) yf[i] = pack_pin((ci[2 * i] - ci[28 + 2 * i]) * gg, (ci[2 * i + 1] - ci[29 + 2 * i]) * gg);
        else yf[i] = pack_pin((ci[2 * i] + ci[36 + 2 * i]) * gg, (ci[2 * i + 1] + ci[37 + 2 * i]) * gg);
      }
      if (tid == 0) PROF_EV(8);
      if (tid == 128) PROF_EV(28);
#pragma unroll 1
      for (int t = 1; t < 7; t += 2) {
        odd_head(t);
        wg_fence();
        tile_mma(IC<32>(), t, OA + 4, 14);
        wg_commit();
        const int zo = t >> 1, owner = rb * 8 + 2 * ((q4 + zo + 1) & 3) + rank;
        uint4* dst = ws->part + (size_t)(owner * 3 + zo) * 1024 + fo;
        auto send = [&] {
          fence_regs<32, 32>(ct);
#pragma unroll
          for (int i = 0; i < 4; i++)
            asm volatile("st.relaxed.gpu.global.v4.u32 [%0], {%1,%2,%3,%4};" ::"l"(dst + i * 32),
                         "r"((add_bf2(pv[i].x, pack_bf16(ct[32 + 8 * i], ct[33 + 8 * i])) & ~1u) | tag), "r"(add_bf2(pv[i].y, pack_bf16(ct[34 + 8 * i], ct[35 + 8 * i]))),
                         "r"(add_bf2(pv[i].z, pack_bf16(ct[36 + 8 * i], ct[37 + 8 * i]))), "r"(add_bf2(pv[i].w, pack_bf16(ct[38 + 8 * i], ct[39 + 8 * i]))) : "memory");
          hint_add_if(lane == 0, &ws->cntP[32 * owner + 8 * (zo + (zo == 2 ? wg : 0))]);
        };
        if (t == 5) fetch(pv, 2);
        twait(bars + 8 * (B_FT + ((t + 1) & 3)), (t + 1) >> 2, t + 1);
        wg_fence();
        tile_mma(IC<0>(), t + 1, 0, TH);
        wg_commit();
        wg_wait<1>();
        mbar_arrive_if(elect && t < 5, bars + 8 * (B_ET + t));
        if (t == 5) send(); else fetch(pv, zo);
        wg_fence();
        tile_mma(IC<0>(), t + 1, TH, EB);
        wg_commit();
        if (t != 5) send();
        wg_fence();
        tile_mma(IC<0>(), t + 1, EB, 14);
        wg_commit();
      }
      {
        uint4 p1[4], p2[4];
        auto acc4 = [&](uint4 (&d)[4], const uint4 (&a)[4]) {
#pragma unroll
          for (int i = 0; i < 4; i++) { d[i].x = add_bf2(d[i].x, a[i].x); d[i].y = add_bf2(d[i].y, a[i].y); d[i].z = add_bf2(d[i].z, a[i].z); d[i].w = add_bf2(d[i].w, a[i].w); }
        };
        auto add32 = [&](const uint4 (&a)[4]) {
#pragma unroll
          for (int i = 0; i < 4; i++) {
            const uint32_t u[4] = {a[i].x, a[i].y, a[i].z, a[i].w};
#pragma unroll
            for (int e = 0; e < 4; e++) { ct[32 + 8 * i + 2 * e] += bf_lo(u[e]); ct[33 + 8 * i + 2 * e] += bf_hi(u[e]); }
          }
        };
        odd_head(7);
        fetch(pv, 4);
        fetch(p1, 5);
        wg_fence();
        tile_mma(IC<32>(), 7, OA + 4, OB);
        wg_commit();
        uint32_t bad = 0;
#pragma unroll
        for (int i = 0; i < 4; i++) { bad |= (pv[i].x ^ tag) | (p1[i].x ^ tag); pv[i].x &= ~1u; p1[i].x &= ~1u; }
        acc4(pv, p1);
        fetch(p1, 3);
        wg_fence();
        tile_mma(IC<32>(), 7, OB, 14);
        wg_commit();
        if (tid == 0) { PROF_EV(9); PROF_CK(46); }
        if (tid == 128) PROF_EV(29);
        fetch(p2, 6);
        if (tid == 0) PROF_EV(24);
        wg_wait<0>();
        fence_regs<32, 32>(ct);
#pragma unroll
        for (int i = 0; i < 4; i++) bad |= p2[i].x ^ tag;
        if (__any_sync(0xffffffffu, bad & 1)) {
          const uint4* src = ws->part + (size_t)(rb * 8 + j) * 3 * 1024 + fo;
          uint4 p0[4];
          int n = 0;
          do {
            bad = 0;
#pragma unroll
            for (int i = 0; i < 4; i++) {
              pv[i] = ld_x4(src + i * 32); p0[i] = ld_x4(src + 1024 + i * 32); p2[i] = ld_x4(src + 2048 + i * 32);
              bad |= (pv[i].x ^ tag) | (p0[i].x ^ tag) | (p2[i].x ^ tag);
            }
            if (++n > (1 << 21)) __trap();
          } while (__any_sync(0xffffffffu, bad & 1));
#pragma unroll
          for (int i = 0; i < 4; i++) { pv[i].x &= ~1u; p0[i].x &= ~1u; }
          acc4(pv, p0);
        }
#pragma unroll
        for (int i = 0; i < 4; i++) p2[i].x &= ~1u;
        acc4(p1, p2);
        add32(pv); add32(p1);
#pragma unroll
        for (int i = 0; i < 4; i++)
          pv[i] = make_uint4(pack_bf16(ct[32 + 8 * i], ct[33 + 8 * i]), pack_bf16(ct[34 + 8 * i], ct[35 + 8 * i]), pack_bf16(ct[36 + 8 * i], ct[37 + 8 * i]), pack_bf16(ct[38 + 8 * i], ct[39 + 8 * i]));
        if (tid == 0) PROF_EV(14);
        const uint32_t stg = sb + OFF_T + warp * 2048;
        const int mr = (lane & 7) + ((lane >> 3) & 1) * 8, mc = lane >> 4;
#pragma unroll
        for (int i = 0; i < 4; i++)
          asm volatile("stmatrix.sync.aligned.m8n8.x4.shared.b16 [%0], {%1,%2,%3,%4};" ::"r"(stg + mr * 128 + (((2 * i + mc) ^ (mr & 7)) << 4)), "r"(pv[i].x),
                       "r"(pv[i].y), "r"(pv[i].z), "r"(pv[i].w) : "memory");
        __syncwarp();
#pragma unroll
        for (int i = 0; i < 4; i++) {
          const int r = 4 * i + (lane >> 3), c = lane & 7;
          const uint4 v = *(const uint4*)(smem + OFF_T + warp * 2048 + r * 128 + ((c ^ (r & 7)) << 4));
          *(uint4*)(out + (size_t)(2 * rb + wg + 32 * (16 * w + r)) * 512 + 64 * (q4 + 4 * rank) + 8 * c) = v;
        }
      }
      if (tid == 0) { PROF_EV(15); PROF_CK(41); }
      if (tid == 128) PROF_EV(30);
    }
  } else if (warp < 12) {
    asm volatile("setmaxnreg.dec.sync.aligned.u32 104;");
    asm volatile("barrier.cluster.arrive.relaxed.aligned;" ::: "memory");
    const int t = tid - 256, w = warp - 8;
    const uint32_t ep = ld_x1(&ws->epoch[blockIdx.x * 8]);
    const uint32_t tag = (ep + 1) & 1;
    auto w_issue = [&](const CUtensorMap* m) {

      if (elect_one()) { mbar_expect_tx(bars + 8 * (B_WR + w), 3072); tma4d(sb + OFF_T + w * 3072, m, bars + 8 * (B_WR + w), 32 * j, 0, 4 * (rb & 1) + w, rb >> 1); }

          __syncwarp();
    };
    auto gate_rows = [&] {
      const int r = 16 * j + 4 * w + (lane >> 3);
      const uint4* pg = (const uint4*)gate_w + (lane & 7);
      {
        float a = 0.f;
        asm volatile("bar.sync 4, 256;" ::: "memory");
#pragma unroll 1
        for (int hf = 0; hf < 2; hf++) {
          uint4 v[4], u[4];
#pragma unroll
          for (int kb = 0; kb < 4; kb++) v[kb] = __ldg(pg + (4 * hf + kb) * 8);
          mbar_wait(bars + 8 * (B_FE + 1 + 2 * hf), 0);
          if (hf) w_issue(&maps.wr);
#pragma unroll
          for (int kb = 0; kb < 4; kb++) u[kb] = *(const uint4*)(smem + (4 * hf + kb) * U + r * 128 + (((lane ^ r) & 7) << 4));
#pragma unroll
          for (int kb = 0; kb < 4; kb++) {
            const uint32_t uu[4] = {u[kb].x, u[kb].y, u[kb].z, u[kb].w}, vv[4] = {v[kb].x, v[kb].y, v[kb].z, v[kb].w};
#pragma unroll
            for (int e = 0; e < 4; e++) {
              uint32_t pr;
              asm("mul.rn.bf16x2 %0, %1, %2;" : "=r"(pr) : "r"(uu[e]), "r"(vv[e]));
              a += bf_lo(pr) + bf_hi(pr);
            }
          }
        }
#pragma unroll
        for (int o = 4; o; o >>= 1) a += __shfl_xor_sync(0xffffffffu, a, o);
        if ((lane & 7) == 0)
          asm volatile("st.relaxed.gpu.global.u32 [%0], %1;" ::"l"(ws->gate + rb * 128 + r),
                       "r"(pack_bf16(0.f, __fdividef(1.0f, 1.0f + __expf(-bf_lo(pack_bf16(a, 0.f))))) | tag) : "memory");
        if (t == 0) PROF_EV(18);
      }
    };
    {
      const int g = lane >> 2, q = lane & 3;
      uint32_t wf[32];
      if (!helper) {
        gate_rows();
        const uint32_t wa = sb + OFF_T + w * (3072 + 2) + (rb & 1) * 8 + q * 96 + g * 4, wb[2] = {wa + (rb & 1) * 32, wa + 32 - (rb & 1) * 32};
#pragma unroll 1
        for (int ri = 0; ri < 2; ri++) {
          mbar_wait(bars + 8 * (B_WR + w), ri);
#pragma unroll
          for (int n2 = 0; n2 < 32 / WB; n2++) {
            uint32_t v[WB];
#pragma unroll
            for (int i = 0; i < WB; i++) {
              const int e = n2 * WB + i;
              asm volatile("ld.shared.u16 %0, [%1];" : "=r"(v[i]) : "r"(wb[e & 1] + ((e >> 1) & 7) * 384 + (e >> 4) * 2) : "memory");
            }
#pragma unroll
            for (int i = 0; i < WB; i++) wf[n2 * WB + i] = __byte_perm(wf[n2 * WB + i], v[i], 0x5432);
            if (WSLEEP) { asm volatile("nanosleep.u32 %0;" ::"r"(WSLEEP + (v[WB - 1] >> 16)) : "memory"); }
          }
          __syncwarp();
          if (ri == 0) w_issue(&maps.wi);
        }
        asm volatile("bar.sync 1, 128;" ::: "memory");
        if (t == 0) PROF_EV(11);
      } else {
        asm volatile("bar.sync 4, 256;" ::: "memory");
        hint_wait(&ws->cntW[0], (ep + 1) * 128u);
        const uint32_t t0 = (uint32_t)clock();
#pragma unroll 1
        for (;;) {
          uint32_t bad = 0;
#pragma unroll
          for (int i = 0; i < 32; i++) {
            const float2 v = ld_x2((const float2*)ws->Wh + (i >> 4) * 2048 + 16 * w + g + 8 * (i & 1) + 64 * q + ((i >> 1) & 7) * 256);
            wf[i] = __float_as_uint(v.x); bad |= __float_as_uint(v.y) ^ tag;
          }
          if (!__any_sync(0xffffffffu, bad & 1)) break;
          spin_guard(t0);
        }
        if (t == 0) PROF_EV(11);
      }
      if (w == 0 && elect_one()) { mbar_expect_tx(bars + 8 * B_W, 8192); bulk_load(sb + OFF_D, dtab, 8192, bars + 8 * B_W); }
      asm volatile("barrier.cluster.wait.aligned;" ::: "memory");
      mbar_wait(bars + 8 * B_W, 0);
      mbar_wait(bars + 8 * B_HX, 0);
      if (t == 0) PROF_EV(12);
      const uint32_t dd = (sb & 0x3FFFF) >> 4;
      const uint64_t dF = d128((dd + (OFF_D >> 4)) | (512u << 16)), dI = d128((dd + (OFF_D >> 4)) | (1u << 16)), dA = d128((dd + (OFF_XB >> 4)) | (512u << 16));
      float az[32];
      const int zero = blockIdx.x >> 16;
      uint32_t pf[32];
#pragma unroll
      for (int mt = 0; mt < 2; mt++) {
        wg_fence();
        if (mt == 0) mma_ss64<0, 3, 0>(az, dA, dF);
        else mma_ss64<0, 3, 2>(az, dA + 512, dF, zero);
#pragma unroll
        for (int k = 1; k < 4; k++) mma_ss64<0, 3, 1>(az, dA + (mt * 512 + k * 128), dF + k * 128);
        wg_commit();
        wg_wait<0>();
        fence_regs<0, 32>(az);
#pragma unroll
        for (int i = 0; i < 16; i++) {
          const float wr = bf_lo(wf[16 * mt + i]), wi = bf_hi(wf[16 * mt + i]);
          pf[16 * mt + i] = pack_pin(fmaf(az[2 * i], wr, -az[2 * i + 1] * wi), fmaf(az[2 * i], wi, az[2 * i + 1] * wr));
        }
      }
      if (t == 0) PROF_EV(16);
      {
        const int m = lane >> 3, r = lane & 7;
        const int sl = 2 * (m >> 1) + ((r >> 1) & 1) + 4 * (r >> 2);
        const uint32_t a0 = sb + OFF_XB + w * 4096 + sl * 64 + (((((m ^ rb) & 1) * 2 + (r & 1)) ^ (sl >> 1)) << 4);
        uint32_t pk[16];
#pragma unroll
        for (int mt = 0; mt < 3; mt++) {
          if (mt < 2) {
            wg_fence();
            mma_rs64<0, 0, 2>(az, pf[16 * mt], pf[16 * mt + 1], pf[16 * mt + 2], pf[16 * mt + 3], dI, mt ? (int)helper : zero);
#pragma unroll
            for (int k = 1; k < 4; k++) mma_rs64<0, 0, 1>(az, pf[16 * mt + 4 * k], pf[16 * mt + 4 * k + 1], pf[16 * mt + 4 * k + 2], pf[16 * mt + 4 * k + 3], dI + k * 2);
            wg_commit();
          }
          if (mt > 0 && !helper) {
#pragma unroll
            for (int i = 0; i < 4; i++) stsm4t(a0 + (mt - 1) * 2048 + i * 512, pk[4 * i], pk[4 * i + 1], pk[4 * i + 2], pk[4 * i + 3]);
          }
          if (mt < 2) {
            wg_wait<0>();
            fence_regs<0, 32>(az);
#pragma unroll
            for (int i = 0; i < 16; i++) pk[i] = pack_pin(az[2 * i], az[2 * i + 1]);
          }
        }
      }
      if (helper) {
#pragma unroll
        for (int i = 0; i < 16; i++) {
          const int n = i >> 1, s0 = 8 * (n >> 1) + 2 * (n & 1) + (q & 1) + 4 * (q >> 1);
          if ((n & 1) == (int)(blockIdx.x & 1)) st_u2(ws->Ts + s0 * 64 + 16 * w + g + 8 * (i & 1), pack_bf16(az[2 * i], az[2 * i + 1]), tag);
        }
        __syncwarp();
        hint_add_if(lane == 0, &ws->cntH[0]);
        if (t == 0) { ws->epoch[blockIdx.x * 8] = ep + 1; PROF_EV(13); }
      } else {
        asm volatile("fence.proxy.async.shared::cta;" ::: "memory");
        __syncwarp();
        if (elect_one()) {
          if (t == 0) PROF_EV(17);
          if (SPACE) __nanosleep(SPACE * w);
          asm volatile("cp.async.bulk.tensor.4d.global.shared::cta.bulk_group [%0, {%2, %3, %4, %5}], [%1];" ::"l"(&maps.ts), "r"(sb + OFF_XB + w * 4096),
                       "r"(32 * rank), "r"(0), "r"(2 * q4), "r"(4 * rb + w) : "memory");
          bulk_done_signal(&ws->cntT[32 * q4]);
          asm volatile("mbarrier.arrive.shared::cluster.b64 _, [%0];" ::"r"(mapa(bars + 8 * B_RD0, rank ^ 1)) : "memory");
          if (t == 96) PROF_EV(13);
        }
        __syncwarp();
        if (j == 0) {
          hint_wait(&ws->cntH[0], (ep + 1) * 8u);
          const uint32_t t0 = (uint32_t)clock();
          float2 v;
          do { v = ld_x2((const float2*)ws->Ts + 2 * rb * 64 + t); spin_guard(t0); } while (__any_sync(0xffffffffu, (__float_as_uint(v.y) ^ tag) & 1));
          mbar_wait(bars + 8 * B_TL, 0);
          const uint32_t u = __float_as_uint(v.x);
          *(uint16_t*)(smem + OFF_T + t * 128 + ((t & 7) << 4)) = (uint16_t)u;
          *(uint16_t*)(smem + OFF_T + t * 128 + (((t & 7) ^ 1) << 4)) = (uint16_t)(u >> 16);
          asm volatile("fence.proxy.async.shared::cta;" ::: "memory");
          __syncwarp();
          mbar_arrive_if(lane == 0, bars + 8 * B_T);
        }
      }
    }
  } else {
    asm volatile("setmaxnreg.dec.sync.aligned.u32 24;");
    auto xf_load = [&](int q) {
      const uint32_t fb = bars + 8 * (B_FX + q);
      mbar_expect_tx(fb, U + 8192);
      tma3d(sb + q * U, &maps.x, fb, 64 * q, 0, 2 * rb);
      if (q >= 4) mbar_wait(bars + 8 * (B_FE + ((q - 4) >> 1)), 0);
      tma2d(sb + OFF_XB + (q & 3) * 8192, &maps.ft, fb, 64 * q, 64 * j);
    };
    if (elect_one()) {
      if (warp == 14) {
#pragma unroll
        for (int i = 0; i < B_FT; i++) mbar_init(bars + 8 * i, 1);
        asm volatile("fence.mbarrier_init.release.cluster;" ::: "memory");
        if (!helper) {
#pragma unroll 1
          for (int n = 0; n < 2; n++) {
            const uint32_t fb = bars + 8 * (B_FA + n);
            xf_load(2 * n); xf_load(2 * n + 1);
            mbar_expect_tx(fb, U);
            tma2d(sb + OFF_RING + n * U, &maps.g64, fb, f_full, 64 * n);
            tma2d(sb + OFF_RING + n * U + 8192, &maps.u64, fb, f_full, 64 * n);
          }
        }
      } else if (warp == 15) {
#pragma unroll
        for (int i = B_FT; i < NBAR; i++) mbar_init(bars + 8 * i, i < B_EA ? 1 : i < B_T ? 2 : 4);
#pragma unroll
        for (int i = 0; i < 8; i++) mbar_expect_tx(bars + 8 * (B_Z + i), U / 2);
        asm volatile("fence.mbarrier_init.release.cluster;" ::: "memory");
        asm volatile("fence.proxy.async.shared::cta;" ::: "memory");
      }
    }
    __syncwarp();
    asm volatile("bar.arrive 0, 384;" ::: "memory");
    asm volatile("bar.arrive 4, 256;" ::: "memory");
    __syncwarp();
    asm volatile("barrier.cluster.arrive.relaxed.aligned;" ::: "memory");
    asm volatile("bar.sync 3, 128;" ::: "memory");
    if (warp == 15 && !helper) {
        mbar_wait(bars + 8 * B_FE, 0);
        const uint32_t tag = (ld_x1(&ws->epoch[blockIdx.x * 8]) + 1) & 1;
        const int c = lane >> 4, jj = 16 * blockIdx.x + (lane & 15), jm = (2048 - jj) & 2047;
        const unsigned short* pr = (const unsigned short*)w_r + 256 * c;
        const unsigned short* pi = (const unsigned short*)w_i + 256 * c;
        const float wr = 0.25f * (bf_lo(__ldg(pr + jj * 257)) + bf_lo(__ldg(pr + jm * 257)));
        const float wi = 0.25f * (bf_lo(__ldg(pi + jj * 257)) - bf_lo(__ldg(pi + jm * 257)));
        st_u2(ws->Wh + c * 2048 + jj, c ? pack_bf16(-wi, wr) : pack_bf16(wr, wi), tag);
        __syncwarp();
        hint_add_if(lane == 0, &ws->cntW[0]);
        mbar_wait(bars + 8 * B_XS, 0);
        const uint32_t t0 = (uint32_t)clock();
        uint4 v;
        do { v = ld_x4(ws->gate + rb * 128 + 4 * lane); spin_guard(t0); } while (__any_sync(0xffffffffu, ((v.x ^ tag) | (v.y ^ tag) | (v.z ^ tag) | (v.w ^ tag)) & 1));
        *(uint4*)(smem + OFF_G + lane * 16) = v;
        __syncwarp();
        mbar_arrive_if(lane < 4, bars + 8 * B_G);
      }
    auto part_load = [&](int i, unsigned ep1) {
      const uint32_t bytes = i < 2 ? U : U / 2;
      mbar_wait(bars + 8 * (B_PZ + (i == 0)), 0);
      mbar_expect_tx(bars + 8 * (B_HP + i), bytes);
      flag_wait(&ws->cntP[32 * (rb * 8 + j) + 8 * i], ep1 * (i < 2 ? 8u : 4u));
      bulk_load(sb + (i == 0 ? OFF_T : i == 1 ? 0 : i * (U / 2)), ws->part + (size_t)(rb * 8 + j) * 3072 + (i < 2 ? i * 1024 : 1024 + i * 512), bytes, bars + 8 * (B_HP + i));
      if (i == 2) PROF_EV(26);
    };
    if ((!helper || warp == 15) && elect_one()) {
      if (warp < 14) {
        const int p = warp - 12;
#pragma unroll 1
        for (int i = 4 + p; i < 14; i += 2) asm volatile("prefetch.tensormap [%0];" ::"l"((const char*)&maps + i * 128) : "memory");
#pragma unroll 1
        for (int n = 2; n < 31; n++) {
          const bool table = n == 4 || n >= 29;
          const bool half = n >= 17 && n < 21;
          const int q = n < 4 ? n : n < 17 ? n - 1 : n - 5;
          const CUtensorMap* m = table ? &maps.e : half ? &maps.g32 + p : &maps.g64 + p;
          const int c0 = table ? 0 : half ? f_half : f_full + 64 * (q >> 3);
          const int c1 = table ? (2 * rb + ((n & 1) ^ 1)) * 128 + 64 * p : half ? 128 * (n - 17) : 64 * (q & 7);
          const uint32_t fb = bars + 8 * (B_FA + (n & 3)), dst = sb + OFF_RING + (n & 3) * U + p * 8192;
          if (n < 4) mbar_wait(bars + 8 * (B_FE + n - 2), 0);
          else mbar_wait(bars + 8 * (B_EA + (n & 3)), ((n >> 2) & 1) ^ 1);
          tma2d(dst, m, fb, c0, c1);
          if (p == 0) mbar_expect_tx(fb, U);
        }
        part_load(2 + p, ld_x1(&ws->epoch[blockIdx.x * 8]) + 1);
      } else if (warp == 15) {
        const unsigned ep1 = ld_x1(&ws->epoch[blockIdx.x * 8]) + 1;
        flag_wait(&ws->cntX[helper ? 0 : 32 * j], ep1 * 16u);
        PROF_EV(22);
        mbar_expect_tx(bars + 8 * B_HX, U);
        bulk_load(sb + OFF_XB, ws->X + (size_t)(helper ? 128 : 16 * j + rb) * 8192, U, bars + 8 * B_HX);
        if (!helper) {
          flag_wait(&ws->cntT[32 * q4], ep1 * 128u);
          PROF_EV(23);
          mbar_expect_tx(bars + 8 * B_TL, U);
          tma3d(sb + OFF_T, &maps.t, bars + 8 * B_TL, 64 * j, 0, 2 * rb);
          part_load(0, ep1); part_load(1, ep1);
          mbar_wait(bars + 8 * (B_HP + 2), 0); mbar_wait(bars + 8 * (B_HP + 3), 0);
          ws->epoch[blockIdx.x * 8] = ep1;
        }
      } else {
#pragma unroll 1
        for (int q = 4; q < 8; q++) xf_load(q);
        mbar_wait(bars + 8 * (B_FE + 2), 0);
        mbar_expect_tx(bars + 8 * B_E0, U);
        tma2d(sb + OFF_XB, &maps.e, bars + 8 * B_E0, 0, 2 * rb * 128);
        tma2d(sb + OFF_XB + 8192, &maps.e, bars + 8 * B_E0, 0, 2 * rb * 128 + 64);
#pragma unroll 1
        for (int h2 = 0; h2 < 2; h2++) {
          const int s0 = 2 * rb + h2, sg = (s0 & ~6) | ((s0 & 2) << 1) | ((s0 & 4) >> 1);
          mbar_wait(bars + 8 * (B_XS + h2), 0);
#pragma unroll 1
          for (int c = 0; c < 2; c++) {
            asm volatile("cp.async.bulk.tensor.4d.global.shared::cta.bulk_group [%0, {%2, %3, %4, %5}], [%1];" ::"l"(&maps.xs),
                         "r"(sb + OFF_XB + h2 * 8192 + c * 4096), "r"(0), "r"(sg), "r"(0), "r"(16 * j + 8 * c) : "memory");
            if (j == 0)
              asm volatile("cp.async.bulk.global.shared::cta.bulk_group [%0], [%1], 256;" ::"l"(ws->X + 128 * 8192 + c * 4096 + sg * 128),
                           "r"(sb + OFF_SP + h2 * 512 + c * 256) : "memory");
            if (SPACE && h2 + c < 2) __nanosleep(SPACE);
          }
        }
        bulk_done_signal(&ws->cntX[32 * j]);
        PROF_EV(20);
#pragma unroll 1
        for (int t = 0; t < 8; t++) {
          const int col = 64 * (((q4 + 1 + (t >> 1)) & 3) + 4 * ((t & 1) ? rank : 1 - rank));
          const uint32_t fb = bars + 8 * (B_FT + (t & 3)), dst = sb + (t & 3) * TB;
          mbar_wait(bars + 8 * (B_ET + (t < 3 ? t + 1 : t & 3)), t >> 2);
          mbar_expect_tx(fb, (t & 1) ? TB : 28672);
          if (t & 1) tma3d(dst + 28672, &maps.fg, fb, col, 16 * rank, 4 * q4);
          tma2d(dst, &maps.d224, fb, col, 224 * j);
        }
      }
    }
  }
}

typedef CUresult (*EncodeFn)(CUtensorMap*, CUtensorMapDataType, cuuint32_t, void*, const cuuint64_t*, const cuuint64_t*, const cuuint32_t*,
                             const cuuint32_t*, CUtensorMapInterleave, CUtensorMapSwizzle, CUtensorMapL2promotion, CUtensorMapFloatOOBfill);

static void encode(EncodeFn f, CUtensorMap* m, const void* base, int rank, const cuuint64_t* dims, const cuuint64_t* strides, const cuuint32_t* box,
                   CUtensorMapSwizzle sw) {
  cuuint32_t es[5] = {1, 1, 1, 1, 1};
  f(m, CU_TENSOR_MAP_DATA_TYPE_BFLOAT16, rank, (void*)base, dims, strides, box, es, CU_TENSOR_MAP_INTERLEAVE_NONE, sw,
    CU_TENSOR_MAP_L2_PROMOTION_L2_128B, CU_TENSOR_MAP_FLOAT_OOB_FILL_NONE);
}

extern "C" void kernel_launch(void* const* d_in, const int* in_sizes, int n_in, void* d_out, int out_size) {
  (void)in_sizes; (void)n_in; (void)out_size;
  const __nv_bfloat16* x = (const __nv_bfloat16*)d_in[0];
  const __nv_bfloat16* w_r = (const __nv_bfloat16*)d_in[1];
  const __nv_bfloat16* w_i = (const __nv_bfloat16*)d_in[2];
  const __nv_bfloat16* Wg = (const __nv_bfloat16*)d_in[4];
  const __nv_bfloat16* Wu = (const __nv_bfloat16*)d_in[5];
  const __nv_bfloat16* Wd = (const __nv_bfloat16*)d_in[6];
  const __nv_bfloat16* gw = (const __nv_bfloat16*)d_in[7];

  void* fp = nullptr; cudaDriverEntryPointQueryResult qr;
  cudaGetDriverEntryPoint("cuTensorMapEncodeTiled", &fp, cudaEnableDefault, &qr);
  EncodeFn enc = (EncodeFn)fp;
  void *pFT, *pET, *pDT, *pW;
  cudaGetSymbolAddress(&pDT, g_DT); cudaGetSymbolAddress(&pW, g_work);
  void *pX = ((Work*)pW)->X, *pT = ((Work*)pW)->T;
  cudaGetSymbolAddress(&pFT, g_FT); cudaGetSymbolAddress(&pET, g_ET);

  Maps mp;
  const CUtensorMapSwizzle S128 = CU_TENSOR_MAP_SWIZZLE_128B, S64 = CU_TENSOR_MAP_SWIZZLE_64B;
  { cuuint64_t d[3] = {512, 64, 32}, s[2] = {32768, 1024}; cuuint32_t b[3] = {64, 64, 2}; encode(enc, &mp.x, x, 3, d, s, b, S128); }
  { cuuint64_t d[2] = {512, 512}, s[1] = {1024}; cuuint32_t b[2] = {64, 64}; encode(enc, &mp.ft, pFT, 2, d, s, b, S128); }
  { cuuint64_t d[4] = {128, 32, 2, 129}, s[3] = {256, 8192, 16384}; cuuint32_t b[4] = {128, 1, 2, 8}; encode(enc, &mp.xs, pX, 4, d, s, b, CU_TENSOR_MAP_SWIZZLE_NONE); }
  { cuuint64_t d[4] = {64, 32, 8, 64}, s[3] = {65536, 128, 1024}; cuuint32_t b[4] = {32, 32, 2, 1}; encode(enc, &mp.ts, pT, 4, d, s, b, S64); }
  { cuuint64_t d[3] = {512, 32, 16}, s[2] = {1024, 32768}; cuuint32_t b[3] = {64, 16, 4}; encode(enc, &mp.fg, pFT, 3, d, s, b, S128); }
  { cuuint64_t d[3] = {512, 64, 32}, s[2] = {1024, 65536}; cuuint32_t b[3] = {64, 64, 2}; encode(enc, &mp.t, pT, 3, d, s, b, S128); }
  { cuuint64_t d[2] = {64, 4096}, s[1] = {128}; cuuint32_t b[2] = {64, 64}; encode(enc, &mp.e, pET, 2, d, s, b, S128); }
  { cuuint64_t d[2] = {1792, 512}, s[1] = {3584}; cuuint32_t b[2] = {64, 64}, b2[2] = {32, 128};
    encode(enc, &mp.g64, Wg, 2, d, s, b, S128); encode(enc, &mp.u64, Wu, 2, d, s, b, S128);
    encode(enc, &mp.g32, Wg, 2, d, s, b2, S64); encode(enc, &mp.u32, Wu, 2, d, s, b2, S64); }
  { cuuint64_t d[2] = {512, 1792}, s[1] = {1024}; cuuint32_t b[2] = {64, 224}; encode(enc, &mp.d224, Wd, 2, d, s, b, S128); }
  { cuuint64_t d[4] = {264, 32, 8, 8}, s[3] = {32896, 512, 4112}; cuuint32_t b[4] = {48, 32, 1, 1};
    encode(enc, &mp.wr, w_r, 4, d, s, b, CU_TENSOR_MAP_SWIZZLE_NONE); encode(enc, &mp.wi, w_i, 4, d, s, b, CU_TENSOR_MAP_SWIZZLE_NONE); }

  cudaFuncSetAttribute(fused_kernel, cudaFuncAttributeMaxDynamicSharedMemorySize, SMEM_BYTES);
  fused_kernel<<<NCTA, 512, SMEM_BYTES>>>((Work*)pW, (const uint16_t*)pDT, w_r, w_i, gw, x, (__nv_bfloat16*)d_out, mp);
}
```

```cpp
#include <cuda_runtime.h>
#include <cuda_bf16.h>
#include <cuda.h>
#include <stdint.h>

namespace tbl {
constexpr double PI = 3.14159265358979323846264338327950288;
constexpr double sin_s(double x) { double t = x, s = x; for (int n = 1; n < 12; n++) { t *= -x * x / ((2 * n) * (2 * n + 1)); s += t; } return s; }
constexpr double cos_s(double x) { double t = 1, s = 1; for (int n = 1; n < 12; n++) { t *= -x * x / ((2 * n - 1) * (2 * n)); s += t; } return s; }
constexpr double cos2048(int m) {
  m &= 2047; if (m > 1024) m = 2048 - m;
  bool neg = false; if (m > 512) { m = 1024 - m; neg = true; }
  double v = (m <= 256) ? cos_s(2 * PI * m / 2048) : sin_s(2 * PI * (512 - m) / 2048);
  return neg ? -v : v;
}
constexpr uint16_t to_bf16(double v) {
  if (v == 0) return 0;
  uint16_t s = 0; if (v < 0) { s = 0x8000; v = -v; }
  int e = 0; while (v >= 2) { v /= 2; e++; } while (v < 1) { v *= 2; e--; }
  double m = (v - 1) * 128; int mi = (int)m; double fr = m - mi;
  if (fr > 0.5 || (fr == 0.5 && (mi & 1))) mi++;
  if (mi == 128) { mi = 0; e++; }
  return (uint16_t)(s | ((e + 127) << 7) | mi);
}
struct CosT { uint16_t v[2048]; constexpr CosT() : v() { for (int i = 0; i < 2048; i++) v[i] = to_bf16(cos2048(i)); } };
struct alignas(1024) FT {
  uint16_t v[512 * 512];
  constexpr FT() : v() {
    CosT c;
    for (int r = 0; r < 512; r++) {
      int k = (r >> 5) * 16 + 2 * (r & 7) + ((r >> 4) & 1), e = (r >> 3) & 1;
      int mul = 4 * k, add = e ? 512 : 0;
      if (k == 0 && e == 1) { mul = 1024; add = 0; }
      for (int d = 0; d < 512; d++) v[r * 512 + d] = c.v[(d * mul + add) & 2047];
    }
  }
};
struct alignas(1024) ET {
  uint16_t v[2048 * 128];
  constexpr ET() : v() {
    CosT c;
    for (int s = 0; s < 2048; s++)
      for (int j = 0; j < 64; j++) {
        const int o = (s & 31) * 8192 + (s >> 5) * 64 + j;
        v[o] = c.v[(s * j) & 2047]; v[o + 4096] = c.v[(s * j + 512) & 2047];
      }
  }
};
struct alignas(1024) DT {
  uint16_t v[64 * 64];
  constexpr DT() : v() {
    CosT c;
    for (int r = 0; r < 64; r++)
      for (int n = 0; n < 64; n++) {
        const int sg = r >> 1, s0 = (sg & ~6) | ((sg & 2) << 1) | ((sg & 4) >> 1), e = r & 1, f = n & 1;
        const int m = 64 * s0 * (n >> 1) + (e == f ? 0 : e ? -512 : 512);
        v[r * 64 + (((n >> 3) ^ (r & 7)) << 3) + (n & 7)] = c.v[m & 2047];
      }
  }
};
}

__device__ constexpr tbl::FT g_FT = tbl::FT();
__device__ constexpr tbl::ET g_ET = tbl::ET();
__device__ constexpr tbl::DT g_DT = tbl::DT();

struct alignas(1024) Work {
  unsigned epoch[132 * 8];
  unsigned cntX[8 * 32], cntT[8 * 32], cntP[128 * 32], cntW[32], cntH[32];
  alignas(16) float gate[16 * 128];
  alignas(16) uint2 Wh[2 * 2048];
  alignas(16) uint2 Ts[32 * 64];
  alignas(1024) uint16_t X[129 * 8192];
  alignas(1024) uint16_t T[32 * 64 * 512];
  alignas(1024) uint4 part[128 * 3 * 1024];
};
__device__ Work g_work;
#define PROF_EV(i) do {} while (0)
#define PROF_CK(i) do {} while (0)

__device__ __forceinline__ uint32_t smem_u32(const void* p) { return (uint32_t)__cvta_generic_to_shared(p); }
__device__ __forceinline__ void mbar_init(uint32_t bar, uint32_t cnt) { asm volatile("mbarrier.init.shared::cta.b64 [%0], %1;" ::"r"(bar), "r"(cnt)); }
__device__ __forceinline__ void mbar_expect_tx(uint32_t bar, uint32_t bytes) { asm volatile("mbarrier.arrive.expect_tx.shared::cta.b64 _, [%0], %1;" ::"r"(bar), "r"(bytes) : "memory"); }
__device__ __forceinline__ void mbar_arrive(uint32_t bar) { asm volatile("mbarrier.arrive.shared::cta.b64 _, [%0];" ::"r"(bar) : "memory"); }
__device__ __forceinline__ bool elect_one() {
  uint32_t p;
  asm volatile("{\n.reg .pred p;\nelect.sync _|p, 0xffffffff;\nselp.u32 %0, 1, 0, p;\n}" : "=r"(p));
  return p;
}
__device__ __forceinline__ void mbar_arrive_if(bool p, uint32_t bar) {
  asm volatile("{\n.reg .pred p;\nsetp.ne.b32 p, %1, 0;\n@p mbarrier.arrive.shared::cta.b64 _, [%0];\n}" ::"r"(bar), "r"((int)p) : "memory");
}
__device__ __forceinline__ void hint_add_if(bool p, unsigned* a) {
  asm volatile("{\n.reg .pred p;\nsetp.ne.b32 p, %1, 0;\n@p red.relaxed.gpu.global.add.u32 [%0], 1;\n}" ::"l"(a), "r"((int)p) : "memory");
}
__device__ __forceinline__ bool mbar_try(uint32_t bar, uint32_t parity) {
  uint32_t ok;
  asm volatile("{\n.reg .pred p;\nmbarrier.test_wait.parity.shared::cta.b64 p, [%1], %2;\nselp.u32 %0, 1, 0, p;\n}" : "=r"(ok) : "r"(bar), "r"(parity) : "memory");
  return ok;
}
__device__ __forceinline__ void mbar_wait(uint32_t bar, uint32_t parity) {
  asm volatile(
      "{\n.reg .pred p;\n.reg .u32 n;\nmov.u32 n, 0;\n"
      "W_LOOP:\nmbarrier.try_wait.parity.shared::cta.b64 p, [%0], %1;\n@p bra W_DONE;\n"
      "add.u32 n, n, 1;\nsetp.lt.u32 p, n, 0x40000;\n@p bra W_LOOP;\ntrap;\nW_DONE:\n}" ::"r"(bar), "r"(parity) : "memory");
}
__device__ __forceinline__ void bulk_load(uint32_t dst, const void* src, uint32_t bytes, uint32_t bar) {
  asm volatile("cp.async.bulk.shared::cluster.global.mbarrier::complete_tx::bytes [%0], [%1], %2, [%3];" ::"r"(dst), "l"(src), "r"(bytes), "r"(bar) : "memory");
}
__device__ __forceinline__ void spin_guard(uint32_t t0) { if ((uint32_t)clock() - t0 > (1u << 30)) __trap(); }
__device__ __forceinline__ float2 ld_x2(const float2* p) { float2 v; asm volatile("ld.relaxed.gpu.global.v2.f32 {%0,%1}, [%2];" : "=f"(v.x), "=f"(v.y) : "l"(p) : "memory"); return v; }
__device__ __forceinline__ void st_u2(uint2* p, uint32_t a, uint32_t b) { asm volatile("st.relaxed.gpu.global.v2.u32 [%0], {%1,%2};" ::"l"(p), "r"(a), "r"(b) : "memory"); }
__device__ __forceinline__ uint32_t ld_x1(const void* p) { uint32_t v; asm volatile("ld.relaxed.gpu.global.u32 %0, [%1];" : "=r"(v) : "l"(p) : "memory"); return v; }
__device__ __forceinline__ uint4 ld_x4(const void* p) { uint4 v; asm volatile("ld.relaxed.gpu.global.v4.u32 {%0,%1,%2,%3}, [%4];" : "=r"(v.x), "=r"(v.y), "=r"(v.z), "=r"(v.w) : "l"(p) : "memory"); return v; }
__device__ __forceinline__ uint32_t mapa(uint32_t a, uint32_t cta) { uint32_t r; asm volatile("mapa.shared::cluster.u32 %0, %1, %2;" : "=r"(r) : "r"(a), "r"(cta)); return r; }
__device__ __forceinline__ void stsm4t(uint32_t a, uint32_t r0, uint32_t r1, uint32_t r2, uint32_t r3) {
  asm volatile("stmatrix.sync.aligned.m8n8.x4.trans.shared.b16 [%0], {%1,%2,%3,%4};" ::"r"(a), "r"(r0), "r"(r1), "r"(r2), "r"(r3) : "memory");
}
__device__ __forceinline__ void hint_add(unsigned* p) { asm volatile("red.relaxed.gpu.global.add.u32 [%0], 1;" ::"l"(p) : "memory"); }
__device__ __forceinline__ void hint_wait(const unsigned* p, unsigned target) {
  const uint32_t t0 = (uint32_t)clock();
  while ((int)(ld_x1(p) - target) < 0) spin_guard(t0);
}
__device__ __forceinline__ void bulk_done_signal(unsigned* p) {
  asm volatile("cp.async.bulk.commit_group;\ncp.async.bulk.wait_group 0;\nfence.proxy.async.global;" ::: "memory");
  hint_add(p);
}
__device__ __forceinline__ void flag_wait(const unsigned* p, unsigned target) {
  hint_wait(p, target);
  asm volatile("fence.proxy.async.global;" ::: "memory");
}
__device__ __forceinline__ void tma2d(uint32_t dst, const CUtensorMap* m, uint32_t bar, int c0, int c1) {
  asm volatile("cp.async.bulk.tensor.2d.shared::cluster.global.mbarrier::complete_tx::bytes [%0], [%1, {%3, %4}], [%2];" ::"r"(dst), "l"(m), "r"(bar), "r"(c0), "r"(c1) : "memory");
}
__device__ __forceinline__ void tma3d(uint32_t dst, const CUtensorMap* m, uint32_t bar, int c0, int c1, int c2) {
  asm volatile("cp.async.bulk.tensor.3d.shared::cluster.global.mbarrier::complete_tx::bytes [%0], [%1, {%3, %4, %5}], [%2];" ::"r"(dst), "l"(m), "r"(bar), "r"(c0), "r"(c1), "r"(c2) : "memory");
}
__device__ __forceinline__ void tma4d(uint32_t dst, const CUtensorMap* m, uint32_t bar, int c0, int c1, int c2, int c3) {
  asm volatile("cp.async.bulk.tensor.4d.shared::cluster.global.mbarrier::complete_tx::bytes [%0], [%1, {%3, %4, %5, %6}], [%2];" ::"r"(dst), "l"(m), "r"(bar), "r"(c0), "r"(c1), "r"(c2), "r"(c3) : "memory");
}
__device__ __forceinline__ void wg_fence() { asm volatile("wgmma.fence.sync.aligned;" ::: "memory"); }
__device__ __forceinline__ void wg_commit() { asm volatile("wgmma.commit_group.sync.aligned;" ::: "memory"); }
template <int N> __device__ __forceinline__ void wg_wait() { asm volatile("wgmma.wait_group.sync.aligned %0;" ::"n"(N) : "memory"); }
template <int O, int N, int NN> __device__ __forceinline__ void fence_regs(float (&d)[NN]) {
#pragma unroll
  for (int i = 0; i < N; i++) asm volatile("" : "+f"(d[O + i])::"memory");
}
__device__ __forceinline__ uint32_t pack_bf16(float lo, float hi) {
  uint32_t r; asm("cvt.rn.bf16x2.f32 %0, %1, %2;" : "=r"(r) : "f"(hi), "f"(lo)); return r;
}
__device__ __forceinline__ uint32_t pack_pin(float lo, float hi) {
  uint32_t r; asm volatile("cvt.rn.bf16x2.f32 %0, %1, %2;" : "=r"(r) : "f"(hi), "f"(lo) : "memory"); return r;
}
__device__ __forceinline__ uint32_t add_bf2(uint32_t a, uint32_t b) { uint32_t r; asm("add.rn.bf16x2 %0, %1, %2;" : "=r"(r) : "r"(a), "r"(b)); return r; }
__device__ __forceinline__ float bf_lo(uint32_t u) { return __uint_as_float(u << 16); }
__device__ __forceinline__ float bf_hi(uint32_t u) { return __uint_as_float(u & 0xffff0000u); }

__device__ __forceinline__ uint64_t d128(uint32_t lo) { uint64_t d; asm("mov.b64 %0, {%1, 0x40000040};" : "=l"(d) : "r"(lo)); return d; }
__device__ __forceinline__ uint64_t d64(uint32_t lo) { uint64_t d; asm("mov.b64 %0, {%1, 0x80000020};" : "=l"(d) : "r"(lo)); return d; }
template<int O,int TB,int ACC,int NN> __device__ __forceinline__ void mma_ss64(float (&d)[NN], uint64_t da, uint64_t db, int sd = 0){
  if constexpr (ACC == 1) asm volatile("wgmma.mma_async.sync.aligned.m64n64k16.f32.bf16.bf16 {%0,%1,%2,%3,%4,%5,%6,%7,%8,%9,%10,%11,%12,%13,%14,%15,%16,%17,%18,%19,%20,%21,%22,%23,%24,%25,%26,%27,%28,%29,%30,%31}, %32, %33, 1, 1, 1, %35, %34;"
   : "+f"(d[O+0]), "+f"(d[O+1]), "+f"(d[O+2]), "+f"(d[O+3]), "+f"(d[O+4]), "+f"(d[O+5]), "+f"(d[O+6]), "+f"(d[O+7]), "+f"(d[O+8]), "+f"(d[O+9]), "+f"(d[O+10]), "+f"(d[O+11]), "+f"(d[O+12]), "+f"(d[O+13]), "+f"(d[O+14]), "+f"(d[O+15]), "+f"(d[O+16]), "+f"(d[O+17]), "+f"(d[O+18]), "+f"(d[O+19]), "+f"(d[O+20]), "+f"(d[O+21]), "+f"(d[O+22]), "+f"(d[O+23]), "+f"(d[O+24]), "+f"(d[O+25]), "+f"(d[O+26]), "+f"(d[O+27]), "+f"(d[O+28]), "+f"(d[O+29]), "+f"(d[O+30]), "+f"(d[O+31])
   : "l"(da), "l"(db), "n"(TB & 1), "n"(TB >> 1));
  else if constexpr (ACC == 0) asm volatile("wgmma.mma_async.sync.aligned.m64n64k16.f32.bf16.bf16 {%0,%1,%2,%3,%4,%5,%6,%7,%8,%9,%10,%11,%12,%13,%14,%15,%16,%17,%18,%19,%20,%21,%22,%23,%24,%25,%26,%27,%28,%29,%30,%31}, %32, %33, 0, 1, 1, %35, %34;"
   : "=f"(d[O+0]), "=f"(d[O+1]), "=f"(d[O+2]), "=f"(d[O+3]), "=f"(d[O+4]), "=f"(d[O+5]), "=f"(d[O+6]), "=f"(d[O+7]), "=f"(d[O+8]), "=f"(d[O+9]), "=f"(d[O+10]), "=f"(d[O+11]), "=f"(d[O+12]), "=f"(d[O+13]), "=f"(d[O+14]), "=f"(d[O+15]), "=f"(d[O+16]), "=f"(d[O+17]), "=f"(d[O+18]), "=f"(d[O+19]), "=f"(d[O+20]), "=f"(d[O+21]), "=f"(d[O+22]), "=f"(d[O+23]), "=f"(d[O+24]), "=f"(d[O+25]), "=f"(d[O+26]), "=f"(d[O+27]), "=f"(d[O+28]), "=f"(d[O+29]), "=f"(d[O+30]), "=f"(d[O+31])
   : "l"(da), "l"(db), "n"(TB & 1), "n"(TB >> 1));
  else asm volatile("{\n.reg .pred p;\nsetp.ne.b32 p, %36, 0;\nwgmma.mma_async.sync.aligned.m64n64k16.f32.bf16.bf16 {%0,%1,%2,%3,%4,%5,%6,%7,%8,%9,%10,%11,%12,%13,%14,%15,%16,%17,%18,%19,%20,%21,%22,%23,%24,%25,%26,%27,%28,%29,%30,%31}, %32, %33, p, 1, 1, %35, %34;\n}"
   : "+f"(d[O+0]), "+f"(d[O+1]), "+f"(d[O+2]), "+f"(d[O+3]), "+f"(d[O+4]), "+f"(d[O+5]), "+f"(d[O+6]), "+f"(d[O+7]), "+f"(d[O+8]), "+f"(d[O+9]), "+f"(d[O+10]), "+f"(d[O+11]), "+f"(d[O+12]), "+f"(d[O+13]), "+f"(d[O+14]), "+f"(d[O+15]), "+f"(d[O+16]), "+f"(d[O+17]), "+f"(d[O+18]), "+f"(d[O+19]), "+f"(d[O+20]), "+f"(d[O+21]), "+f"(d[O+22]), "+f"(d[O+23]), "+f"(d[O+24]), "+f"(d[O+25]), "+f"(d[O+26]), "+f"(d[O+27]), "+f"(d[O+28]), "+f"(d[O+29]), "+f"(d[O+30]), "+f"(d[O+31])
   : "l"(da), "l"(db), "n"(TB & 1), "n"(TB >> 1), "r"(sd));
}
template<int O,int TB,int ACC,int NN> __device__ __forceinline__ void mma_rs64(float (&d)[NN], uint32_t a0, uint32_t a1, uint32_t a2, uint32_t a3, uint64_t db, int sd = 0){
  if constexpr (ACC == 1) asm volatile("wgmma.mma_async.sync.aligned.m64n64k16.f32.bf16.bf16 {%0,%1,%2,%3,%4,%5,%6,%7,%8,%9,%10,%11,%12,%13,%14,%15,%16,%17,%18,%19,%20,%21,%22,%23,%24,%25,%26,%27,%28,%29,%30,%31}, {%32,%33,%34,%35}, %36, 1, 1, 1, %37;"
   : "+f"(d[O+0]), "+f"(d[O+1]), "+f"(d[O+2]), "+f"(d[O+3]), "+f"(d[O+4]), "+f"(d[O+5]), "+f"(d[O+6]), "+f"(d[O+7]), "+f"(d[O+8]), "+f"(d[O+9]), "+f"(d[O+10]), "+f"(d[O+11]), "+f"(d[O+12]), "+f"(d[O+13]), "+f"(d[O+14]), "+f"(d[O+15]), "+f"(d[O+16]), "+f"(d[O+17]), "+f"(d[O+18]), "+f"(d[O+19]), "+f"(d[O+20]), "+f"(d[O+21]), "+f"(d[O+22]), "+f"(d[O+23]), "+f"(d[O+24]), "+f"(d[O+25]), "+f"(d[O+26]), "+f"(d[O+27]), "+f"(d[O+28]), "+f"(d[O+29]), "+f"(d[O+30]), "+f"(d[O+31])
   : "r"(a0), "r"(a1), "r"(a2), "r"(a3), "l"(db), "n"(TB));
  else if constexpr (ACC == 0) asm volatile("wgmma.mma_async.sync.aligned.m64n64k16.f32.bf16.bf16 {%0,%1,%2,%3,%4,%5,%6,%7,%8,%9,%10,%11,%12,%13,%14,%15,%16,%17,%18,%19,%20,%21,%22,%23,%24,%25,%26,%27,%28,%29,%30,%31}, {%32,%33,%34,%35}, %36, 0, 1, 1, %37;"
   : "=f"(d[O+0]), "=f"(d[O+1]), "=f"(d[O+2]), "=f"(d[O+3]), "=f"(d[O+4]), "=f"(d[O+5]), "=f"(d[O+6]), "=f"(d[O+7]), "=f"(d[O+8]), "=f"(d[O+9]), "=f"(d[O+10]), "=f"(d[O+11]), "=f"(d[O+12]), "=f"(d[O+13]), "=f"(d[O+14]), "=f"(d[O+15]), "=f"(d[O+16]), "=f"(d[O+17]), "=f"(d[O+18]), "=f"(d[O+19]), "=f"(d[O+20]), "=f"(d[O+21]), "=f"(d[O+22]), "=f"(d[O+23]), "=f"(d[O+24]), "=f"(d[O+25]), "=f"(d[O+26]), "=f"(d[O+27]), "=f"(d[O+28]), "=f"(d[O+29]), "=f"(d[O+30]), "=f"(d[O+31])
   : "r"(a0), "r"(a1), "r"(a2), "r"(a3), "l"(db), "n"(TB));
  else asm volatile("{\n.reg .pred p;\nsetp.ne.b32 p, %38, 0;\nwgmma.mma_async.sync.aligned.m64n64k16.f32.bf16.bf16 {%0,%1,%2,%3,%4,%5,%6,%7,%8,%9,%10,%11,%12,%13,%14,%15,%16,%17,%18,%19,%20,%21,%22,%23,%24,%25,%26,%27,%28,%29,%30,%31}, {%32,%33,%34,%35}, %36, p, 1, 1, %37;\n}"
   : "+f"(d[O+0]), "+f"(d[O+1]), "+f"(d[O+2]), "+f"(d[O+3]), "+f"(d[O+4]), "+f"(d[O+5]), "+f"(d[O+6]), "+f"(d[O+7]), "+f"(d[O+8]), "+f"(d[O+9]), "+f"(d[O+10]), "+f"(d[O+11]), "+f"(d[O+12]), "+f"(d[O+13]), "+f"(d[O+14]), "+f"(d[O+15]), "+f"(d[O+16]), "+f"(d[O+17]), "+f"(d[O+18]), "+f"(d[O+19]), "+f"(d[O+20]), "+f"(d[O+21]), "+f"(d[O+22]), "+f"(d[O+23]), "+f"(d[O+24]), "+f"(d[O+25]), "+f"(d[O+26]), "+f"(d[O+27]), "+f"(d[O+28]), "+f"(d[O+29]), "+f"(d[O+30]), "+f"(d[O+31])
   : "r"(a0), "r"(a1), "r"(a2), "r"(a3), "l"(db), "n"(TB), "r"(sd));
}
template<int O,int TB,int ACC,int NN> __device__ __forceinline__ void mma_ss128(float (&d)[NN], uint64_t da, uint64_t db, int sd = 0){
  if constexpr (ACC == 1) asm volatile("wgmma.mma_async.sync.aligned.m64n128k16.f32.bf16.bf16 {%0,%1,%2,%3,%4,%5,%6,%7,%8,%9,%10,%11,%12,%13,%14,%15,%16,%17,%18,%19,%20,%21,%22,%23,%24,%25,%26,%27,%28,%29,%30,%31,%32,%33,%34,%35,%36,%37,%38,%39,%40,%41,%42,%43,%44,%45,%46,%47,%48,%49,%50,%51,%52,%53,%54,%55,%56,%57,%58,%59,%60,%61,%62,%63}, %64, %65, 1, 1, 1, %67, %66;"
   : "+f"(d[O+0]), "+f"(d[O+1]), "+f"(d[O+2]), "+f"(d[O+3]), "+f"(d[O+4]), "+f"(d[O+5]), "+f"(d[O+6]), "+f"(d[O+7]), "+f"(d[O+8]), "+f"(d[O+9]), "+f"(d[O+10]), "+f"(d[O+11]), "+f"(d[O+12]), "+f"(d[O+13]), "+f"(d[O+14]), "+f"(d[O+15]), "+f"(d[O+16]), "+f"(d[O+17]), "+f"(d[O+18]), "+f"(d[O+19]), "+f"(d[O+20]), "+f"(d[O+21]), "+f"(d[O+22]), "+f"(d[O+23]), "+f"(d[O+24]), "+f"(d[O+25]), "+f"(d[O+26]), "+f"(d[O+27]), "+f"(d[O+28]), "+f"(d[O+29]), "+f"(d[O+30]), "+f"(d[O+31]), "+f"(d[O+32]), "+f"(d[O+33]), "+f"(d[O+34]), "+f"(d[O+35]), "+f"(d[O+36]), "+f"(d[O+37]), "+f"(d[O+38]), "+f"(d[O+39]), "+f"(d[O+40]), "+f"(d[O+41]), "+f"(d[O+42]), "+f"(d[O+43]), "+f"(d[O+44]), "+f"(d[O+45]), "+f"(d[O+46]), "+f"(d[O+47]), "+f"(d[O+48]), "+f"(d[O+49]), "+f"(d[O+50]), "+f"(d[O+51]), "+f"(d[O+52]), "+f"(d[O+53]), "+f"(d[O+54]), "+f"(d[O+55]), "+f"(d[O+56]), "+f"(d[O+57]), "+f"(d[O+58]), "+f"(d[O+59]), "+f"(d[O+60]), "+f"(d[O+61]), "+f"(d[O+62]), "+f"(d[O+63])
   : "l"(da), "l"(db), "n"(TB & 1), "n"(TB >> 1));
  else if constexpr (ACC == 0) asm volatile("wgmma.mma_async.sync.aligned.m64n128k16.f32.bf16.bf16 {%0,%1,%2,%3,%4,%5,%6,%7,%8,%9,%10,%11,%12,%13,%14,%15,%16,%17,%18,%19,%20,%21,%22,%23,%24,%25,%26,%27,%28,%29,%30,%31,%32,%33,%34,%35,%36,%37,%38,%39,%40,%41,%42,%43,%44,%45,%46,%47,%48,%49,%50,%51,%52,%53,%54,%55,%56,%57,%58,%59,%60,%61,%62,%63}, %64, %65, 0, 1, 1, %67, %66;"
   : "=f"(d[O+0]), "=f"(d[O+1]), "=f"(d[O+2]), "=f"(d[O+3]), "=f"(d[O+4]), "=f"(d[O+5]), "=f"(d[O+6]), "=f"(d[O+7]), "=f"(d[O+8]), "=f"(d[O+9]), "=f"(d[O+10]), "=f"(d[O+11]), "=f"(d[O+12]), "=f"(d[O+13]), "=f"(d[O+14]), "=f"(d[O+15]), "=f"(d[O+16]), "=f"(d[O+17]), "=f"(d[O+18]), "=f"(d[O+19]), "=f"(d[O+20]), "=f"(d[O+21]), "=f"(d[O+22]), "=f"(d[O+23]), "=f"(d[O+24]), "=f"(d[O+25]), "=f"(d[O+26]), "=f"(d[O+27]), "=f"(d[O+28]), "=f"(d[O+29]), "=f"(d[O+30]), "=f"(d[O+31]), "=f"(d[O+32]), "=f"(d[O+33]), "=f"(d[O+34]), "=f"(d[O+35]), "=f"(d[O+36]), "=f"(d[O+37]), "=f"(d[O+38]), "=f"(d[O+39]), "=f"(d[O+40]), "=f"(d[O+41]), "=f"(d[O+42]), "=f"(d[O+43]), "=f"(d[O+44]), "=f"(d[O+45]), "=f"(d[O+46]), "=f"(d[O+47]), "=f"(d[O+48]), "=f"(d[O+49]), "=f"(d[O+50]), "=f"(d[O+51]), "=f"(d[O+52]), "=f"(d[O+53]), "=f"(d[O+54]), "=f"(d[O+55]), "=f"(d[O+56]), "=f"(d[O+57]), "=f"(d[O+58]), "=f"(d[O+59]), "=f"(d[O+60]), "=f"(d[O+61]), "=f"(d[O+62]), "=f"(d[O+63])
   : "l"(da), "l"(db), "n"(TB & 1), "n"(TB >> 1));
  else asm volatile("{\n.reg .pred p;\nsetp.ne.b32 p, %68, 0;\nwgmma.mma_async.sync.aligned.m64n128k16.f32.bf16.bf16 {%0,%1,%2,%3,%4,%5,%6,%7,%8,%9,%10,%11,%12,%13,%14,%15,%16,%17,%18,%19,%20,%21,%22,%23,%24,%25,%26,%27,%28,%29,%30,%31,%32,%33,%34,%35,%36,%37,%38,%39,%40,%41,%42,%43,%44,%45,%46,%47,%48,%49,%50,%51,%52,%53,%54,%55,%56,%57,%58,%59,%60,%61,%62,%63}, %64, %65, p, 1, 1, %67, %66;\n}"
   : "+f"(d[O+0]), "+f"(d[O+1]), "+f"(d[O+2]), "+f"(d[O+3]), "+f"(d[O+4]), "+f"(d[O+5]), "+f"(d[O+6]), "+f"(d[O+7]), "+f"(d[O+8]), "+f"(d[O+9]), "+f"(d[O+10]), "+f"(d[O+11]), "+f"(d[O+12]), "+f"(d[O+13]), "+f"(d[O+14]), "+f"(d[O+15]), "+f"(d[O+16]), "+f"(d[O+17]), "+f"(d[O+18]), "+f"(d[O+19]), "+f"(d[O+20]), "+f"(d[O+21]), "+f"(d[O+22]), "+f"(d[O+23]), "+f"(d[O+24]), "+f"(d[O+25]), "+f"(d[O+26]), "+f"(d[O+27]), "+f"(d[O+28]), "+f"(d[O+29]), "+f"(d[O+30]), "+f"(d[O+31]), "+f"(d[O+32]), "+f"(d[O+33]), "+f"(d[O+34]), "+f"(d[O+35]), "+f"(d[O+36]), "+f"(d[O+37]), "+f"(d[O+38]), "+f"(d[O+39]), "+f"(d[O+40]), "+f"(d[O+41]), "+f"(d[O+42]), "+f"(d[O+43]), "+f"(d[O+44]), "+f"(d[O+45]), "+f"(d[O+46]), "+f"(d[O+47]), "+f"(d[O+48]), "+f"(d[O+49]), "+f"(d[O+50]), "+f"(d[O+51]), "+f"(d[O+52]), "+f"(d[O+53]), "+f"(d[O+54]), "+f"(d[O+55]), "+f"(d[O+56]), "+f"(d[O+57]), "+f"(d[O+58]), "+f"(d[O+59]), "+f"(d[O+60]), "+f"(d[O+61]), "+f"(d[O+62]), "+f"(d[O+63])
   : "l"(da), "l"(db), "n"(TB & 1), "n"(TB >> 1), "r"(sd));
}
template<int O,int TB,int ACC,int NN> __device__ __forceinline__ void mma_rs128(float (&d)[NN], uint32_t a0, uint32_t a1, uint32_t a2, uint32_t a3, uint64_t db, int sd = 0){
  if constexpr (ACC == 1) asm volatile("wgmma.mma_async.sync.aligned.m64n128k16.f32.bf16.bf16 {%0,%1,%2,%3,%4,%5,%6,%7,%8,%9,%10,%11,%12,%13,%14,%15,%16,%17,%18,%19,%20,%21,%22,%23,%24,%25,%26,%27,%28,%29,%30,%31,%32,%33,%34,%35,%36,%37,%38,%39,%40,%41,%42,%43,%44,%45,%46,%47,%48,%49,%50,%51,%52,%53,%54,%55,%56,%57,%58,%59,%60,%61,%62,%63}, {%64,%65,%66,%67}, %68, 1, 1, 1, %69;"
   : "+f"(d[O+0]), "+f"(d[O+1]), "+f"(d[O+2]), "+f"(d[O+3]), "+f"(d[O+4]), "+f"(d[O+5]), "+f"(d[O+6]), "+f"(d[O+7]), "+f"(d[O+8]), "+f"(d[O+9]), "+f"(d[O+10]), "+f"(d[O+11]), "+f"(d[O+12]), "+f"(d[O+13]), "+f"(d[O+14]), "+f"(d[O+15]), "+f"(d[O+16]), "+f"(d[O+17]), "+f"(d[O+18]), "+f"(d[O+19]), "+f"(d[O+20]), "+f"(d[O+21]), "+f"(d[O+22]), "+f"(d[O+23]), "+f"(d[O+24]), "+f"(d[O+25]), "+f"(d[O+26]), "+f"(d[O+27]), "+f"(d[O+28]), "+f"(d[O+29]), "+f"(d[O+30]), "+f"(d[O+31]), "+f"(d[O+32]), "+f"(d[O+33]), "+f"(d[O+34]), "+f"(d[O+35]), "+f"(d[O+36]), "+f"(d[O+37]), "+f"(d[O+38]), "+f"(d[O+39]), "+f"(d[O+40]), "+f"(d[O+41]), "+f"(d[O+42]), "+f"(d[O+43]), "+f"(d[O+44]), "+f"(d[O+45]), "+f"(d[O+46]), "+f"(d[O+47]), "+f"(d[O+48]), "+f"(d[O+49]), "+f"(d[O+50]), "+f"(d[O+51]), "+f"(d[O+52]), "+f"(d[O+53]), "+f"(d[O+54]), "+f"(d[O+55]), "+f"(d[O+56]), "+f"(d[O+57]), "+f"(d[O+58]), "+f"(d[O+59]), "+f"(d[O+60]), "+f"(d[O+61]), "+f"(d[O+62]), "+f"(d[O+63])
   : "r"(a0), "r"(a1), "r"(a2), "r"(a3), "l"(db), "n"(TB));
  else if constexpr (ACC == 0) asm volatile("wgmma.mma_async.sync.aligned.m64n128k16.f32.bf16.bf16 {%0,%1,%2,%3,%4,%5,%6,%7,%8,%9,%10,%11,%12,%13,%14,%15,%16,%17,%18,%19,%20,%21,%22,%23,%24,%25,%26,%27,%28,%29,%30,%31,%32,%33,%34,%35,%36,%37,%38,%39,%40,%41,%42,%43,%44,%45,%46,%47,%48,%49,%50,%51,%52,%53,%54,%55,%56,%57,%58,%59,%60,%61,%62,%63}, {%64,%65,%66,%67}, %68, 0, 1, 1, %69;"
   : "=f"(d[O+0]), "=f"(d[O+1]), "=f"(d[O+2]), "=f"(d[O+3]), "=f"(d[O+4]), "=f"(d[O+5]), "=f"(d[O+6]), "=f"(d[O+7]), "=f"(d[O+8]), "=f"(d[O+9]), "=f"(d[O+10]), "=f"(d[O+11]), "=f"(d[O+12]), "=f"(d[O+13]), "=f"(d[O+14]), "=f"(d[O+15]), "=f"(d[O+16]), "=f"(d[O+17]), "=f"(d[O+18]), "=f"(d[O+19]), "=f"(d[O+20]), "=f"(d[O+21]), "=f"(d[O+22]), "=f"(d[O+23]), "=f"(d[O+24]), "=f"(d[O+25]), "=f"(d[O+26]), "=f"(d[O+27]), "=f"(d[O+28]), "=f"(d[O+29]), "=f"(d[O+30]), "=f"(d[O+31]), "=f"(d[O+32]), "=f"(d[O+33]), "=f"(d[O+34]), "=f"(d[O+35]), "=f"(d[O+36]), "=f"(d[O+37]), "=f"(d[O+38]), "=f"(d[O+39]), "=f"(d[O+40]), "=f"(d[O+41]), "=f"(d[O+42]), "=f"(d[O+43]), "=f"(d[O+44]), "=f"(d[O+45]), "=f"(d[O+46]), "=f"(d[O+47]), "=f"(d[O+48]), "=f"(d[O+49]), "=f"(d[O+50]), "=f"(d[O+51]), "=f"(d[O+52]), "=f"(d[O+53]), "=f"(d[O+54]), "=f"(d[O+55]), "=f"(d[O+56]), "=f"(d[O+57]), "=f"(d[O+58]), "=f"(d[O+59]), "=f"(d[O+60]), "=f"(d[O+61]), "=f"(d[O+62]), "=f"(d[O+63])
   : "r"(a0), "r"(a1), "r"(a2), "r"(a3), "l"(db), "n"(TB));
  else asm volatile("{\n.reg .pred p;\nsetp.ne.b32 p, %70, 0;\nwgmma.mma_async.sync.aligned.m64n128k16.f32.bf16.bf16 {%0,%1,%2,%3,%4,%5,%6,%7,%8,%9,%10,%11,%12,%13,%14,%15,%16,%17,%18,%19,%20,%21,%22,%23,%24,%25,%26,%27,%28,%29,%30,%31,%32,%33,%34,%35,%36,%37,%38,%39,%40,%41,%42,%43,%44,%45,%46,%47,%48,%49,%50,%51,%52,%53,%54,%55,%56,%57,%58,%59,%60,%61,%62,%63}, {%64,%65,%66,%67}, %68, p, 1, 1, %69;\n}"
   : "+f"(d[O+0]), "+f"(d[O+1]), "+f"(d[O+2]), "+f"(d[O+3]), "+f"(d[O+4]), "+f"(d[O+5]), "+f"(d[O+6]), "+f"(d[O+7]), "+f"(d[O+8]), "+f"(d[O+9]), "+f"(d[O+10]), "+f"(d[O+11]), "+f"(d[O+12]), "+f"(d[O+13]), "+f"(d[O+14]), "+f"(d[O+15]), "+f"(d[O+16]), "+f"(d[O+17]), "+f"(d[O+18]), "+f"(d[O+19]), "+f"(d[O+20]), "+f"(d[O+21]), "+f"(d[O+22]), "+f"(d[O+23]), "+f"(d[O+24]), "+f"(d[O+25]), "+f"(d[O+26]), "+f"(d[O+27]), "+f"(d[O+28]), "+f"(d[O+29]), "+f"(d[O+30]), "+f"(d[O+31]), "+f"(d[O+32]), "+f"(d[O+33]), "+f"(d[O+34]), "+f"(d[O+35]), "+f"(d[O+36]), "+f"(d[O+37]), "+f"(d[O+38]), "+f"(d[O+39]), "+f"(d[O+40]), "+f"(d[O+41]), "+f"(d[O+42]), "+f"(d[O+43]), "+f"(d[O+44]), "+f"(d[O+45]), "+f"(d[O+46]), "+f"(d[O+47]), "+f"(d[O+48]), "+f"(d[O+49]), "+f"(d[O+50]), "+f"(d[O+51]), "+f"(d[O+52]), "+f"(d[O+53]), "+f"(d[O+54]), "+f"(d[O+55]), "+f"(d[O+56]), "+f"(d[O+57]), "+f"(d[O+58]), "+f"(d[O+59]), "+f"(d[O+60]), "+f"(d[O+61]), "+f"(d[O+62]), "+f"(d[O+63])
   : "r"(a0), "r"(a1), "r"(a2), "r"(a3), "l"(db), "n"(TB), "r"(sd));
}

#define NEARLY 0
#define XAHEAD 3
#define HEADN 6
#define WBATCH 1
#define WB 8
#define WSLEEP 20
#define XSPREAD 4
#define NOSEND 0
#define MSPLIT 2
#define PFALL 1
#define L2PF 0
#define STAG 1
#define EPF 2
#define XNB 2
#define FNB 0
#define GNB 0
#define TH 4
#define PF0 4
#define FSPLIT 1
#define MGLU 1
#define SPC 2
#define TL 14
#define GKB 4
#define T0A 6
#define T0B 10
#define TGATE 1
#define ZLATE 0
#define EARLYADD 0
#define OA 4
#define OB 11
#define EB 9
#define SPACE 100
#define WPF 1
#define WAFTER 7
#define WPACE 0
#define GATE_AT 4
#define TPACE 40
#define PFMODE 0
#define MAPMODE 1
template <int V> struct IC { static constexpr int value = V; };
struct Maps { CUtensorMap x, ft, g64, u64, e, wr, wi, xs, ts, t, g32, u32, d224, fg; };

constexpr int NCTA = 130;
constexpr int U = 16384;
constexpr int TB = 36864;
constexpr int OFF_RING = 8 * U, OFF_Z = 12 * U, OFF_XB = 12 * U, OFF_T = 13 * U, OFF_D = OFF_T;
constexpr int OFF_BAR = 14 * U, OFF_SP = OFF_BAR + 512, OFF_G = OFF_SP + 1024 + 128;
constexpr int SMEM_BYTES = OFF_G + 512;
constexpr int B_FX = 0, B_FA = 8, B_FT = 12, B_Z = 16, B_W = 24, B_HX = 25, B_TL = 26, B_HP = 27, B_WR = 31, B_E0 = 35;
constexpr int B_EA = 36, B_ET = 40, B_PZ = 44, B_RDY = 46, B_FE = 47;
constexpr int B_T = 51, B_XS = 52, B_G = 54, B_RD0 = 55, NBAR = 56;
__host__ __device__ constexpr int rslot(int n) { return n & 3; }
__host__ __device__ constexpr int rpar(int n) { return (n >> 2) & 1; }

__global__ void __cluster_dims__(2, 1, 1) __launch_bounds__(512, 1)
fused_kernel(Work* __restrict__ ws, const uint16_t* __restrict__ dtab, const __nv_bfloat16* __restrict__ w_r, const __nv_bfloat16* __restrict__ w_i,
             const __nv_bfloat16* __restrict__ gate_w, const __nv_bfloat16* __restrict__ x, __nv_bfloat16* __restrict__ out,
             const __grid_constant__ Maps maps) {
  extern __shared__ __align__(1024) uint8_t smem[];
  if (threadIdx.x < 32 && elect_one()) {
#pragma unroll
    for (int i = 0; i < PF0; i++) asm volatile("prefetch.tensormap [%0];" ::"l"((const char*)&maps + i * 128) : "memory");
  }
  const uint32_t sb = smem_u32(smem);
  const uint32_t bars = sb + OFF_BAR;
  const int tid = threadIdx.x, lane = tid & 31;
  const int warp = __shfl_sync(0xffffffffu, tid >> 5, 0);
  const bool helper = blockIdx.x >= 128;
  const int cl = (blockIdx.x >> 1) & 63, rank = blockIdx.x & 1;
  const int q4 = (cl & 1) | ((cl >> 2) & 2), rb = ((cl >> 1) & 3) | ((cl >> 4) << 2);
  const int j = 2 * q4 + rank;
  const int f_full = 448 * q4 + (rank ? 256 : 0);
  const int f_half = 448 * q4 + (rank ? 224 : 192);

  if (tid == 64) { PROF_EV(0); PROF_CK(40); }
  if (warp < 8) {
    if (!helper && tid < 32) {
      const int r = 16 * j + (tid & 15);
      asm volatile("prefetch.global.L2 [%0];" ::"l"(x + (size_t)(2 * rb + (r >> 6) + 32 * (r & 63)) * 512 + 64 * (tid >> 4)));
    }
    asm volatile("barrier.cluster.arrive.relaxed.aligned;" ::: "memory");
    asm volatile("setmaxnreg.inc.sync.aligned.u32 192;");
    if (!helper) {
      const int wg = warp >> 2, w = warp & 3, g = lane >> 2;
      const bool elect = (tid & 127) == 0;
      float cX[32], cA[64], cB[64], cC[64], ci[64], ct[64];
      const int zero = blockIdx.x >> 16;
      uint32_t h[56], yf[16];
      const uint32_t d0 = (sb & 0x3FFFF) >> 4;
      const uint32_t dK = d0 | (1u << 16), dN = d0 | (512u << 16);
      const uint32_t dX = dK + wg * 512;
      constexpr uint32_t RING = OFF_RING >> 4;
      auto waitA = [&](int n) { mbar_wait(bars + 8 * (B_FA + rslot(n)), rpar(n)); };
      auto freeA = [&](int n) { mbar_arrive_if(elect, bars + 8 * (B_EA + rslot(n))); };
      auto nop = [] {};

      asm volatile("bar.sync 0, 384;" ::: "memory");
#pragma unroll 1
      for (int i = 0; i < 4; i++) {
        const uint64_t dx = d128(dX + i * 2048), df = d128(dK + (OFF_XB >> 4) + (i & 1) * 1024);
        mbar_wait(bars + 8 * (B_FX + 2 * i), 0);
        wg_fence();
        mma_ss64<0, 0, 2>(cX, df, dx, i);
        mma_ss64<0, 0, 1>(cX, df + 2, dx + 2);
        wg_commit(); wg_wait<1>();
        mbar_arrive_if(elect && i, bars + 8 * (B_EA + rslot(i - 1)));
        mma_ss64<0, 0, 1>(cX, df + 4, dx + 4);
        mma_ss64<0, 0, 1>(cX, df + 6, dx + 6);
        if (i == 0 && tid == 0) PROF_EV(1);
        mbar_wait(bars + 8 * (B_FX + 2 * i + 1), 0);
        wg_fence();
#pragma unroll
        for (int k = 0; k < 4; k++) mma_ss64<0, 0, 1>(cX, df + (512 + k * 2), dx + (1024 + k * 2));
        wg_commit();
        waitA(i);
        wg_fence();
        const uint64_t da = d128(dX + i * 1024), db = d128(dN + RING + i * 1024);
        mma_ss128<0, 1, 2>(cA, da, db, i);
        wg_commit(); wg_wait<1>();
        mbar_arrive_if(elect, bars + 8 * (B_FE + i));
#pragma unroll
        for (int k = 1; k < 4; k++) mma_ss128<0, 1, 1>(cA, da + k * 2, db + k * 128);
        wg_commit();
      }
      fence_regs<0, 32>(cX);
#pragma unroll
      for (int e = 0; e < 16; e++) yf[e] = pack_pin(cX[2 * e], cX[2 * e + 1]);
      if (tid == 0) { PROF_EV(2); PROF_CK(42); }
      {
        waitA(4); mbar_wait(bars + 8 * B_E0, 0);
        const uint64_t de = d128(dN + (wg ? RING : OFF_XB >> 4));
        wg_fence();
        mma_rs128<0, 1, 0>(cB, yf[0], yf[1], yf[2], yf[3], de);
        wg_commit();
        wg_wait<1>();
        freeA(3);
#pragma unroll
        for (int k = 1; k < 4; k++) mma_rs128<0, 1, 1>(cB, yf[4 * k], yf[4 * k + 1], yf[4 * k + 2], yf[4 * k + 3], de + k * 128);
        wg_commit();
      }
      bool rel = false;
      auto acquire = [&](int n) {
        rel = elect;
        if (!mbar_try(bars + 8 * (B_FA + rslot(n)), rpar(n))) { wg_wait<0>(); freeA(n - 1); rel = false; waitA(n); }
      };
      auto freeP = [&](int n) { mbar_arrive_if(rel, bars + 8 * (B_EA + rslot(n - 1))); };
      auto ffn_step = [&](auto first, auto split, float (&acc)[64], int n, int kb, auto done, auto work) {
        constexpr int SPLIT = decltype(split)::value;
        acquire(n);
        wg_fence();
        const uint64_t dx = d128(dX + kb * 1024), db = d128(dN + RING + rslot(n) * 1024);
        mma_ss128<0, 1, decltype(first)::value>(acc, dx, db, kb);
#pragma unroll
        for (int k = 1; k < SPLIT; k++) mma_ss128<0, 1, 1>(acc, dx + k * 2, db + k * 128);
        wg_commit();
        work();
        wg_wait<1>();
        freeP(n);
        done();
        if (SPLIT < 4) {
          wg_fence();
#pragma unroll
          for (int k = SPLIT; k < 4; k++) mma_ss128<0, 1, 1>(acc, dx + k * 2, db + k * 128);
          wg_commit();
        }
      };
      {
        const int s0 = 2 * rb + wg, kr = 2 * ((s0 & 1) | ((s0 & 4) >> 1));
        const int m = lane >> 3, r = lane & 7;
        const uint32_t a0 = sb + OFF_XB + wg * 8192 + ((2 * (m >> 1) + (r >> 2)) * 2 + (w & 1)) * 256 + (m & 1) * 128 + (((2 * (r & 3) + ((w >> 1) ^ (r >> 2))) ^ (kr + (m & 1))) << 4);
        ffn_step(IC<1>(), IC<4>(), cA, 5, 4, [&] { fence_regs<0, 64>(cB); }, nop);
        asm volatile("bar.sync 5, 256;" ::: "memory");
        auto stage = [&](int i) {
          stsm4t(a0 + i * 2048, pack_bf16(cB[8 * i] - cB[34 + 8 * i], cB[8 * i + 1] - cB[35 + 8 * i]),
                 pack_bf16(cB[32 + 8 * i] + cB[8 * i + 2], cB[33 + 8 * i] + cB[8 * i + 3]),
                 pack_bf16(cB[8 * i + 4] - cB[38 + 8 * i], cB[8 * i + 5] - cB[39 + 8 * i]),
                 pack_bf16(cB[36 + 8 * i] + cB[8 * i + 6], cB[37 + 8 * i] + cB[8 * i + 7]));
          if (j == 0 && w == 0) {
            const uint32_t a1 = r ? sb + OFF_SP + 1024 : sb + OFF_SP + wg * 512 + (m & 1) * 256 + (m >> 1) * 128;
#pragma unroll
            for (int n = 2 * i; n < 2 * i + 2; n++)
              asm volatile("stmatrix.sync.aligned.m8n8.x4.shared.b16 [%0], {%1,%2,%3,%4};" ::"r"(a1 + ((n ^ (kr + (m >> 1)) ^ r) << 4)),
                           "r"(pack_bf16(cB[4 * n], cB[4 * n + 1])), "r"(pack_bf16(cB[4 * n + 2], cB[4 * n + 3])),
                           "r"(pack_bf16(cB[32 + 4 * n], cB[33 + 4 * n])), "r"(pack_bf16(cB[34 + 4 * n], cB[35 + 4 * n])) : "memory");
          }
        };
        auto publish = [&] {
          asm volatile("fence.proxy.async.shared::cta;" ::: "memory");
          __syncwarp();
          mbar_arrive_if(lane == 0, bars + 8 * (B_XS + wg));
          if (tid == 0) PROF_EV(3);
        };
        stage(0);
        ffn_step(IC<1>(), IC<FSPLIT>(), cA, 6, 5, nop, nop);
        stage(1);
        ffn_step(IC<1>(), IC<FSPLIT>(), cA, 7, 6, nop, nop);
        stage(2);
        ffn_step(IC<1>(), IC<2>(), cA, 8, 7, [&] { stage(3); }, nop);
        publish();
      }
      uint32_t gb0 = 0, gb1 = 0;
      uint32_t ob[2] = {0, 0};
      auto glu = [&](auto& acc, int half, int ho, int i0, int i1) {
#pragma unroll
        for (int i = i0; i < i1; i++)
          asm volatile("{\n.reg .b32 a, b;\ncvt.rn.relu.bf16x2.f32 a, %2, %1;\ncvt.rn.bf16x2.f32 b, %4, %3;\nmul.rn.bf16x2 a, a, b;\nmul.rn.bf16x2 %0, a, %5;\n}"
                       : "=r"(h[ho + i]) : "f"(acc[2 * i]), "f"(acc[2 * i + 1]), "f"(acc[half + 2 * i]), "f"(acc[half + 1 + 2 * i]), "r"(ob[i & 1]) : "memory");
      };
      ffn_step(IC<2>(), IC<1>(), cB, 9, zero, nop, nop);
#pragma unroll 1
      for (int kb = 1; kb < 8; kb++)
        ffn_step(IC<1>(), IC<FSPLIT>(), cB, 9 + kb, kb, nop, [&] {
          if (kb == GKB) {
            mbar_wait(bars + 8 * B_G, 0);
            asm volatile("ld.shared.u32 %0, [%2];\nld.shared.u32 %1, [%2+32];" : "=r"(gb0), "=r"(gb1) : "r"(sb + OFF_G + (wg * 64 + w * 16 + g) * 4) : "memory");
          } else if (kb == 5 + 2 * wg) {
            ob[0] = pack_bf16(1.0f - bf_hi(gb0), 1.0f - bf_hi(gb0)); ob[1] = pack_bf16(1.0f - bf_hi(gb1), 1.0f - bf_hi(gb1));
            glu(cA, 32, 0, 0, 16);
          }
        });
      const uint32_t tag = gb0 & 1;
      const float g0 = bf_hi(gb0), g1 = bf_hi(gb1);
      if (tid == 0) { PROF_EV(4); PROF_CK(43); }
      auto m_step = [&](auto first, int i) {
        acquire(17 + i);
        wg_fence();
        const uint64_t dx = d128(dX + i * 2048), dm = d64(dN + RING + rslot(17 + i) * 1024);
        mma_ss64<0, 1, decltype(first)::value>(ct, dx, dm);
#pragma unroll
        for (int k = 1; k < MSPLIT; k++) mma_ss64<0, 1, 1>(ct, dx + ((k >> 2) * 1024 + (k & 3) * 2), dm + k * 64);
        wg_commit();
        wg_wait<1>();
        freeP(17 + i);
        wg_fence();
#pragma unroll
        for (int k = MSPLIT; k < 8; k++) mma_ss64<0, 1, 1>(ct, dx + ((k >> 2) * 1024 + (k & 3) * 2), dm + k * 64);
        wg_commit();
      };
      m_step(IC<0>(), 0);
#pragma unroll 1
      for (int i = 1; i < 5; i++) {
        if (i == 1 + 2 * wg) glu(cB, 32, 16, 0, 16);
        if (i < 4) m_step(IC<1>(), i);
      }
      if (tid == 0) { PROF_EV(5); PROF_CK(44); }
      ffn_step(IC<0>(), IC<1>(), cC, 21, 0, nop, nop);
#pragma unroll 1
      for (int kb = 1; kb < 8; kb++)
        ffn_step(IC<1>(), IC<FSPLIT>(), cC, 21 + kb, kb, [&] { mbar_arrive_if(elect && !(kb & 1), bars + 8 * (B_ET + (kb >> 1) - 1)); }, [&] {
          if (kb == 1 + wg) glu(ct, 16, 48, 0, 8);
        });

      auto twait = [&](uint32_t bar, uint32_t par, int) { mbar_wait(bar, par); };
      const int fo = warp * 128 + lane;
      auto fetch = [&](uint4 (&pv)[4], int z) {
        twait(bars + 8 * (z < 4 ? B_Z + 2 * z + wg : z < 6 ? B_HP + z - 4 : B_HP + 2 + wg), 0, 8 + z);
        const uint8_t* src = smem + (z < 4 ? OFF_Z - z * U : z == 4 ? OFF_T : (z - 5) * U) + fo * 16;
#pragma unroll
        for (int i = 0; i < 4; i++) pv[i] = *(const uint4*)(src + i * 512);
      };
      const uint32_t peerZ = mapa(sb + OFF_Z + fo * 16, rank ^ 1), peerB = mapa(bars + 8 * (B_Z + wg), rank ^ 1);
      auto tile_mma = [&](auto off, int t, int k0, int k1) {
        constexpr int O = decltype(off)::value;
        const uint64_t db = d128(dN + (t & 3) * (TB >> 4)), dw = db + rank * 256, dm = db + (rank ? 0 : 1536);
#pragma unroll
        for (int k = k0; k < k1; k++) {
          if (k == 0 && O == 0) mma_rs64<O, 1, 2>(ct, h[0], h[1], h[2], h[3], dw, zero);
          else if (k < 14) mma_rs64<O, 1, 1>(ct, h[4 * k], h[4 * k + 1], h[4 * k + 2], h[4 * k + 3], k < 12 ? dw + k * 128 : dm + (k - 12) * 128);
          else if (k == 14) mma_rs64<O, 1, 2>(ct, yf[0], yf[1], yf[2], yf[3], db + k * 128, zero);
          else mma_rs64<O, 1, 1>(ct, yf[4 * k - 56], yf[4 * k - 55], yf[4 * k - 54], yf[4 * k - 53], db + k * 128);
        }
      };
      uint4 pv[4];
      const uint32_t sgn = rank ? 0x80008000u : 0u;
      auto even_end = [&](int t, int k0) {
        wg_fence();
        tile_mma(IC<32>(), t, 14, 18);
        wg_commit();
        tile_mma(IC<0>(), t, k0, 14);
        wg_commit();
        wg_wait<1>();
        fence_regs<32, 32>(ct);
#pragma unroll
        for (int i = 0; i < 4; i++)
          pv[i] = make_uint4(pack_pin(ct[32 + 8 * i], ct[33 + 8 * i]) ^ sgn, pack_pin(ct[34 + 8 * i], ct[35 + 8 * i]) ^ sgn,
                             pack_pin(ct[36 + 8 * i], ct[37 + 8 * i]) ^ sgn, pack_pin(ct[38 + 8 * i], ct[39 + 8 * i]) ^ sgn);
      };
      auto odd_head = [&](int t) {
        twait(bars + 8 * (B_FT + (t & 3)), t >> 2, t);
        wg_fence();
        tile_mma(IC<32>(), t, 0, OA);
        wg_commit();
        if (t < 4) twait(bars + 8 * (t == 1 ? B_RD0 : B_RDY), 0, 14 + t);
        wg_wait<1>();
        mbar_arrive_if(elect && t < 6, bars + 8 * (B_ET + t - 1));
        fence_regs<0, 32>(ct);
        wg_fence();
#pragma unroll
        for (int i = 0; i < 4; i++) {
          asm volatile("st.async.weak.shared::cluster.mbarrier::complete_tx::bytes.v4.b32 [%0], {%2,%3,%4,%5}, [%1];" ::"r"(peerZ - (t >> 1) * U + i * 512),
                       "r"(peerB + 16 * (t >> 1)), "r"(add_bf2(pv[i].x, pack_bf16(ct[8 * i], ct[8 * i + 1]))), "r"(add_bf2(pv[i].y, pack_bf16(ct[8 * i + 2], ct[8 * i + 3]))),
                       "r"(add_bf2(pv[i].z, pack_bf16(ct[8 * i + 4], ct[8 * i + 5]))), "r"(add_bf2(pv[i].w, pack_bf16(ct[8 * i + 6], ct[8 * i + 7]))) : "memory");
          tile_mma(IC<32>(), t, OA + i, OA + i + 1);
        }
        wg_commit();
      };
      asm volatile("barrier.cluster.wait.aligned;" ::: "memory");
      twait(bars + 8 * B_FT, 0, 0);
      if (wg) asm volatile("bar.sync 6, 256;" ::: "memory");
      wg_fence();
      tile_mma(IC<0>(), 0, 0, T0A);
      wg_commit();
      if (!wg) asm volatile("bar.arrive 6, 256;" ::: "memory");
      waitA(29 + wg);
      wg_wait<1>();
      mbar_arrive_if(elect, bars + 8 * (B_ET + 3));
      glu(cC, 32, 32, 0, 16);
      if (tid == 0) PROF_EV(6);
      if (tid == 128) PROF_EV(27);
      mbar_wait(bars + 8 * (j == 0 ? B_T : B_TL), 0);
      if (tid == 0) { PROF_EV(7); PROF_CK(45); }
      wg_fence();
      {
        const uint64_t dt = d128(dN + (OFF_T >> 4) + wg * 512), de = d128(dK + RING + (1 + wg) * 1024);
        mma_ss64<0, 1, 0>(ci, de, dt);
        mma_ss64<32, 1, 0>(ci, de + 512, dt);
#pragma unroll
        for (int k = 1; k < 4; k++) {
          mma_ss64<0, 1, 1>(ci, de + k * 2, dt + k * 128);
          mma_ss64<32, 1, 1>(ci, de + (512 + k * 2), dt + k * 128);
        }
        wg_commit();
      }
      tile_mma(IC<0>(), 0, T0A, T0B);
      wg_commit();
      wg_wait<1>();
      if (elect) asm volatile("mbarrier.arrive.shared::cluster.b64 _, [%0];" ::"r"(mapa(bars + 8 * B_RDY, rank ^ 1)) : "memory");
      mbar_arrive_if(elect, bars + 8 * (B_PZ + 1));
      fence_regs<0, 64>(ci);
#pragma unroll
      for (int i = 0; i < 16; i++) {
        const float gg = ((i & 1) ? g1 : g0) * (2.0f / (2048.0f * 512.0f));
        if (i & 2) yf[i] = pack_pin((ci[2 * i] - ci[28 + 2 * i]) * gg, (ci[2 * i + 1] - ci[29 + 2 * i]) * gg);
        else yf[i] = pack_pin((ci[2 * i] + ci[36 + 2 * i]) * gg, (ci[2 * i + 1] + ci[37 + 2 * i]) * gg);
      }
      even_end(0, T0B);
      if (tid == 0) PROF_EV(8);
      if (tid == 128) PROF_EV(28);
#pragma unroll 1
      for (int t = 1; t < 7; t += 2) {
        odd_head(t);
        wg_fence();
        tile_mma(IC<32>(), t, OA + 4, 14);
        wg_commit();
        const int zo = t >> 1, owner = rb * 8 + 2 * ((q4 + zo + 1) & 3) + rank;
        uint4* dst = ws->part + (size_t)(owner * 3 + zo) * 1024 + fo;
        auto send = [&] {
          fence_regs<32, 32>(ct);
#pragma unroll
          for (int i = 0; i < 4; i++)
            asm volatile("st.relaxed.gpu.global.v4.u32 [%0], {%1,%2,%3,%4};" ::"l"(dst + i * 32),
                         "r"((add_bf2(pv[i].x, pack_bf16(ct[32 + 8 * i], ct[33 + 8 * i])) & ~1u) | tag), "r"(add_bf2(pv[i].y, pack_bf16(ct[34 + 8 * i], ct[35 + 8 * i]))),
                         "r"(add_bf2(pv[i].z, pack_bf16(ct[36 + 8 * i], ct[37 + 8 * i]))), "r"(add_bf2(pv[i].w, pack_bf16(ct[38 + 8 * i], ct[39 + 8 * i]))) : "memory");
          hint_add_if(lane == 0, &ws->cntP[32 * owner + 8 * (zo + (zo == 2 ? wg : 0))]);
        };
        if (t == 5) fetch(pv, 2);
        twait(bars + 8 * (B_FT + ((t + 1) & 3)), (t + 1) >> 2, t + 1);
        wg_fence();
        tile_mma(IC<0>(), t + 1, 0, TH);
        wg_commit();
        wg_wait<1>();
        mbar_arrive_if(elect && t < 5, bars + 8 * (B_ET + t));
        if (t == 5) send(); else fetch(pv, zo);
        wg_fence();
        tile_mma(IC<0>(), t + 1, TH, EB);
        wg_commit();
        if (t != 5) send();
        even_end(t + 1, EB);
      }
      {
        uint4 p1[4], p2[4];
        auto acc4 = [&](uint4 (&d)[4], const uint4 (&a)[4]) {
#pragma unroll
          for (int i = 0; i < 4; i++) { d[i].x = add_bf2(d[i].x, a[i].x); d[i].y = add_bf2(d[i].y, a[i].y); d[i].z = add_bf2(d[i].z, a[i].z); d[i].w = add_bf2(d[i].w, a[i].w); }
        };
        auto add32 = [&](const uint4 (&a)[4]) {
#pragma unroll
          for (int i = 0; i < 4; i++) {
            const uint32_t u[4] = {a[i].x, a[i].y, a[i].z, a[i].w};
#pragma unroll
            for (int e = 0; e < 4; e++) { ct[32 + 8 * i + 2 * e] += bf_lo(u[e]); ct[33 + 8 * i + 2 * e] += bf_hi(u[e]); }
          }
        };
        odd_head(7);
        fetch(pv, 4);
        fetch(p1, 5);
        wg_fence();
        tile_mma(IC<32>(), 7, OA + 4, OB);
        wg_commit();
        uint32_t bad = 0;
#pragma unroll
        for (int i = 0; i < 4; i++) { bad |= (pv[i].x ^ tag) | (p1[i].x ^ tag); pv[i].x &= ~1u; p1[i].x &= ~1u; }
        acc4(pv, p1);
        fetch(p1, 3);
        wg_fence();
        tile_mma(IC<32>(), 7, OB, 14);
        wg_commit();
        if (tid == 0) { PROF_EV(9); PROF_CK(46); }
        if (tid == 128) PROF_EV(29);
        fetch(p2, 6);
        if (tid == 0) PROF_EV(24);
        wg_wait<0>();
        fence_regs<32, 32>(ct);
#pragma unroll
        for (int i = 0; i < 4; i++) bad |= p2[i].x ^ tag;
        if (__any_sync(0xffffffffu, bad & 1)) {
          const uint4* src = ws->part + (size_t)(rb * 8 + j) * 3 * 1024 + fo;
          uint4 p0[4];
          int n = 0;
          do {
            bad = 0;
#pragma unroll
            for (int i = 0; i < 4; i++) {
              pv[i] = ld_x4(src + i * 32); p0[i] = ld_x4(src + 1024 + i * 32); p2[i] = ld_x4(src + 2048 + i * 32);
              bad |= (pv[i].x ^ tag) | (p0[i].x ^ tag) | (p2[i].x ^ tag);
            }
            if (++n > (1 << 21)) __trap();
          } while (__any_sync(0xffffffffu, bad & 1));
#pragma unroll
          for (int i = 0; i < 4; i++) { pv[i].x &= ~1u; p0[i].x &= ~1u; }
          acc4(pv, p0);
        }
#pragma unroll
        for (int i = 0; i < 4; i++) p2[i].x &= ~1u;
        acc4(p1, p2);
        add32(pv); add32(p1);
#pragma unroll
        for (int i = 0; i < 4; i++)
          pv[i] = make_uint4(pack_bf16(ct[32 + 8 * i], ct[33 + 8 * i]), pack_bf16(ct[34 + 8 * i], ct[35 + 8 * i]), pack_bf16(ct[36 + 8 * i], ct[37 + 8 * i]), pack_bf16(ct[38 + 8 * i], ct[39 + 8 * i]));
        if (tid == 0) PROF_EV(14);
        const uint32_t stg = sb + OFF_T + warp * 2048;
        const int mr = (lane & 7) + ((lane >> 3) & 1) * 8, mc = lane >> 4;
#pragma unroll
        for (int i = 0; i < 4; i++)
          asm volatile("stmatrix.sync.aligned.m8n8.x4.shared.b16 [%0], {%1,%2,%3,%4};" ::"r"(stg + mr * 128 + (((2 * i + mc) ^ (mr & 7)) << 4)), "r"(pv[i].x),
                       "r"(pv[i].y), "r"(pv[i].z), "r"(pv[i].w) : "memory");
        __syncwarp();
#pragma unroll
        for (int i = 0; i < 4; i++) {
          const int r = 4 * i + (lane >> 3), c = lane & 7;
          const uint4 v = *(const uint4*)(smem + OFF_T + warp * 2048 + r * 128 + ((c ^ (r & 7)) << 4));
          *(uint4*)(out + (size_t)(2 * rb + wg + 32 * (16 * w + r)) * 512 + 64 * (q4 + 4 * rank) + 8 * c) = v;
        }
      }
      if (tid == 0) { PROF_EV(15); PROF_CK(41); }
      if (tid == 128) PROF_EV(30);
    }
  } else if (warp < 12) {
    asm volatile("setmaxnreg.dec.sync.aligned.u32 104;");
    asm volatile("barrier.cluster.arrive.relaxed.aligned;" ::: "memory");
    const int t = tid - 256, w = warp - 8;
    const uint32_t ep = ld_x1(&ws->epoch[blockIdx.x * 8]);
    const uint32_t tag = (ep + 1) & 1;
    auto w_issue = [&](const CUtensorMap* m) {

      if (elect_one()) { mbar_expect_tx(bars + 8 * (B_WR + w), 3072); tma4d(sb + OFF_T + w * 3072, m, bars + 8 * (B_WR + w), 32 * j, 0, 4 * (rb & 1) + w, rb >> 1); }

          __syncwarp();
    };
    auto gate_rows = [&] {
      const int r = 16 * j + 4 * w + (lane >> 3);
      const uint4* pg = (const uint4*)gate_w + (lane & 7);
      {
        float a = 0.f;
        asm volatile("bar.sync 4, 256;" ::: "memory");
#pragma unroll 1
        for (int hf = 0; hf < 2; hf++) {
          uint4 v[4], u[4];
#pragma unroll
          for (int kb = 0; kb < 4; kb++) v[kb] = __ldg(pg + (4 * hf + kb) * 8);
          mbar_wait(bars + 8 * (B_FE + 1 + 2 * hf), 0);
          if (hf) w_issue(&maps.wr);
#pragma unroll
          for (int kb = 0; kb < 4; kb++) u[kb] = *(const uint4*)(smem + (4 * hf + kb) * U + r * 128 + (((lane ^ r) & 7) << 4));
#pragma unroll
          for (int kb = 0; kb < 4; kb++) {
            const uint32_t uu[4] = {u[kb].x, u[kb].y, u[kb].z, u[kb].w}, vv[4] = {v[kb].x, v[kb].y, v[kb].z, v[kb].w};
#pragma unroll
            for (int e = 0; e < 4; e++) {
              uint32_t pr;
              asm("mul.rn.bf16x2 %0, %1, %2;" : "=r"(pr) : "r"(uu[e]), "r"(vv[e]));
              a += bf_lo(pr) + bf_hi(pr);
            }
          }
        }
#pragma unroll
        for (int o = 4; o; o >>= 1) a += __shfl_xor_sync(0xffffffffu, a, o);
        if ((lane & 7) == 0)
          asm volatile("st.relaxed.gpu.global.u32 [%0], %1;" ::"l"(ws->gate + rb * 128 + r),
                       "r"(pack_bf16(0.f, __fdividef(1.0f, 1.0f + __expf(-bf_lo(pack_bf16(a, 0.f))))) | tag) : "memory");
        if (t == 0) PROF_EV(18);
      }
    };
    {
      const int g = lane >> 2, q = lane & 3;
      uint32_t wf[32];
      if (!helper) {
        gate_rows();
        const uint32_t wa = sb + OFF_T + w * (3072 + 2) + (rb & 1) * 8 + q * 96 + g * 4, wb[2] = {wa + (rb & 1) * 32, wa + 32 - (rb & 1) * 32};
#pragma unroll 1
        for (int ri = 0; ri < 2; ri++) {
          mbar_wait(bars + 8 * (B_WR + w), ri);
#pragma unroll
          for (int n2 = 0; n2 < 32 / WB; n2++) {
            uint32_t v[WB];
#pragma unroll
            for (int i = 0; i < WB; i++) {
              const int e = n2 * WB + i;
              asm volatile("ld.shared.u16 %0, [%1];" : "=r"(v[i]) : "r"(wb[e & 1] + ((e >> 1) & 7) * 384 + (e >> 4) * 2) : "memory");
            }
#pragma unroll
            for (int i = 0; i < WB; i++) wf[n2 * WB + i] = __byte_perm(wf[n2 * WB + i], v[i], 0x5432);
            if (WSLEEP) { asm volatile("nanosleep.u32 %0;" ::"r"(WSLEEP + (v[WB - 1] >> 16)) : "memory"); }
          }
          __syncwarp();
          if (ri == 0) w_issue(&maps.wi);
        }
        asm volatile("bar.sync 1, 128;" ::: "memory");
        if (t == 0) PROF_EV(11);
      } else {
        asm volatile("bar.sync 4, 256;" ::: "memory");
        hint_wait(&ws->cntW[0], (ep + 1) * 128u);
        const uint32_t t0 = (uint32_t)clock();
#pragma unroll 1
        for (;;) {
          uint32_t bad = 0;
#pragma unroll
          for (int i = 0; i < 32; i++) {
            const float2 v = ld_x2((const float2*)ws->Wh + (i >> 4) * 2048 + 16 * w + g + 8 * (i & 1) + 64 * q + ((i >> 1) & 7) * 256);
            wf[i] = __float_as_uint(v.x); bad |= __float_as_uint(v.y) ^ tag;
          }
          if (!__any_sync(0xffffffffu, bad & 1)) break;
          spin_guard(t0);
        }
        if (t == 0) PROF_EV(11);
      }
      if (w == 0 && elect_one()) { mbar_expect_tx(bars + 8 * B_W, 8192); bulk_load(sb + OFF_D, dtab, 8192, bars + 8 * B_W); }
      asm volatile("barrier.cluster.wait.aligned;" ::: "memory");
      mbar_wait(bars + 8 * B_W, 0);
      mbar_wait(bars + 8 * B_HX, 0);
      if (t == 0) PROF_EV(12);
      const uint32_t dd = (sb & 0x3FFFF) >> 4;
      const uint64_t dF = d128((dd + (OFF_D >> 4)) | (512u << 16)), dI = d128((dd + (OFF_D >> 4)) | (1u << 16)), dA = d128((dd + (OFF_XB >> 4)) | (512u << 16));
      float az[32];
      const int zero = blockIdx.x >> 16;
      uint32_t pf[32];
#pragma unroll
      for (int mt = 0; mt < 2; mt++) {
        wg_fence();
        if (mt == 0) mma_ss64<0, 3, 0>(az, dA, dF);
        else mma_ss64<0, 3, 2>(az, dA + 512, dF, zero);
#pragma unroll
        for (int k = 1; k < 4; k++) mma_ss64<0, 3, 1>(az, dA + (mt * 512 + k * 128), dF + k * 128);
        wg_commit();
        wg_wait<0>();
        fence_regs<0, 32>(az);
#pragma unroll
        for (int i = 0; i < 16; i++) {
          const float wr = bf_lo(wf[16 * mt + i]), wi = bf_hi(wf[16 * mt + i]);
          pf[16 * mt + i] = pack_pin(fmaf(az[2 * i], wr, -az[2 * i + 1] * wi), fmaf(az[2 * i], wi, az[2 * i + 1] * wr));
        }
      }
      if (t == 0) PROF_EV(16);
      {
        const int m = lane >> 3, r = lane & 7;
        const int sl = 2 * (m >> 1) + ((r >> 1) & 1) + 4 * (r >> 2);
        const uint32_t a0 = sb + OFF_XB + w * 4096 + sl * 64 + (((((m ^ rb) & 1) * 2 + (r & 1)) ^ (sl >> 1)) << 4);
        uint32_t pk[16];
#pragma unroll
        for (int mt = 0; mt < 3; mt++) {
          if (mt < 2) {
            wg_fence();
            mma_rs64<0, 0, 2>(az, pf[16 * mt], pf[16 * mt + 1], pf[16 * mt + 2], pf[16 * mt + 3], dI, mt ? (int)helper : zero);
#pragma unroll
            for (int k = 1; k < 4; k++) mma_rs64<0, 0, 1>(az, pf[16 * mt + 4 * k], pf[16 * mt + 4 * k + 1], pf[16 * mt + 4 * k + 2], pf[16 * mt + 4 * k + 3], dI + k * 2);
            wg_commit();
          }
          if (mt > 0 && !helper) {
#pragma unroll
            for (int i = 0; i < 4; i++) stsm4t(a0 + (mt - 1) * 2048 + i * 512, pk[4 * i], pk[4 * i + 1], pk[4 * i + 2], pk[4 * i + 3]);
          }
          if (mt < 2) {
            wg_wait<0>();
            fence_regs<0, 32>(az);
#pragma unroll
            for (int i = 0; i < 16; i++) pk[i] = pack_pin(az[2 * i], az[2 * i + 1]);
          }
        }
      }
      if (helper) {
#pragma unroll
        for (int i = 0; i < 16; i++) {
          const int n = i >> 1, s0 = 8 * (n >> 1) + 2 * (n & 1) + (q & 1) + 4 * (q >> 1);
          if ((n & 1) == (int)(blockIdx.x & 1)) st_u2(ws->Ts + s0 * 64 + 16 * w + g + 8 * (i & 1), pack_bf16(az[2 * i], az[2 * i + 1]), tag);
        }
        __syncwarp();
        hint_add_if(lane == 0, &ws->cntH[0]);
        if (t == 0) { ws->epoch[blockIdx.x * 8] = ep + 1; PROF_EV(13); }
      } else {
        asm volatile("fence.proxy.async.shared::cta;" ::: "memory");
        __syncwarp();
        if (elect_one()) {
          if (t == 0) PROF_EV(17);
          if (SPACE) __nanosleep(SPACE * w);
          asm volatile("cp.async.bulk.tensor.4d.global.shared::cta.bulk_group [%0, {%2, %3, %4, %5}], [%1];" ::"l"(&maps.ts), "r"(sb + OFF_XB + w * 4096),
                       "r"(32 * rank), "r"(0), "r"(2 * q4), "r"(4 * rb + w) : "memory");
          bulk_done_signal(&ws->cntT[32 * q4]);
          asm volatile("mbarrier.arrive.shared::cluster.b64 _, [%0];" ::"r"(mapa(bars + 8 * B_RD0, rank ^ 1)) : "memory");
          if (t == 96) PROF_EV(13);
        }
        __syncwarp();
        if (j == 0) {
          hint_wait(&ws->cntH[0], (ep + 1) * 8u);
          const uint32_t t0 = (uint32_t)clock();
          float2 v;
          do { v = ld_x2((const float2*)ws->Ts + 2 * rb * 64 + t); spin_guard(t0); } while (__any_sync(0xffffffffu, (__float_as_uint(v.y) ^ tag) & 1));
          mbar_wait(bars + 8 * B_TL, 0);
          const uint32_t u = __float_as_uint(v.x);
          *(uint16_t*)(smem + OFF_T + t * 128 + ((t & 7) << 4)) = (uint16_t)u;
          *(uint16_t*)(smem + OFF_T + t * 128 + (((t & 7) ^ 1) << 4)) = (uint16_t)(u >> 16);
          asm volatile("fence.proxy.async.shared::cta;" ::: "memory");
          __syncwarp();
          mbar_arrive_if(lane == 0, bars + 8 * B_T);
        }
      }
    }
  } else {
    asm volatile("setmaxnreg.dec.sync.aligned.u32 24;");
    auto xf_load = [&](int q) {
      const uint32_t fb = bars + 8 * (B_FX + q);
      mbar_expect_tx(fb, U + 8192);
      tma3d(sb + q * U, &maps.x, fb, 64 * q, 0, 2 * rb);
      if (q >= 4) mbar_wait(bars + 8 * (B_FE + ((q - 4) >> 1)), 0);
      tma2d(sb + OFF_XB + (q & 3) * 8192, &maps.ft, fb, 64 * q, 64 * j);
    };
    if (elect_one()) {
      if (warp == 14) {
#pragma unroll
        for (int i = 0; i < B_FT; i++) mbar_init(bars + 8 * i, 1);
        asm volatile("fence.mbarrier_init.release.cluster;" ::: "memory");
        if (!helper) {
#pragma unroll 1
          for (int n = 0; n < 2; n++) {
            const uint32_t fb = bars + 8 * (B_FA + n);
            xf_load(2 * n); xf_load(2 * n + 1);
            mbar_expect_tx(fb, U);
            tma2d(sb + OFF_RING + n * U, &maps.g64, fb, f_full, 64 * n);
            tma2d(sb + OFF_RING + n * U + 8192, &maps.u64, fb, f_full, 64 * n);
          }
        }
      } else if (warp == 15) {
#pragma unroll
        for (int i = B_FT; i < NBAR; i++) mbar_init(bars + 8 * i, i < B_EA ? 1 : i < B_T ? 2 : 4);
#pragma unroll
        for (int i = 0; i < 8; i++) mbar_expect_tx(bars + 8 * (B_Z + i), U / 2);
        asm volatile("fence.mbarrier_init.release.cluster;" ::: "memory");
        asm volatile("fence.proxy.async.shared::cta;" ::: "memory");
      }
    }
    __syncwarp();
    asm volatile("bar.arrive 0, 384;" ::: "memory");
    asm volatile("bar.arrive 4, 256;" ::: "memory");
    __syncwarp();
    asm volatile("barrier.cluster.arrive.relaxed.aligned;" ::: "memory");
    asm volatile("bar.sync 3, 128;" ::: "memory");
    if (warp == 15 && !helper) {
        mbar_wait(bars + 8 * B_FE, 0);
        const uint32_t tag = (ld_x1(&ws->epoch[blockIdx.x * 8]) + 1) & 1;
        const int c = lane >> 4, jj = 16 * blockIdx.x + (lane & 15), jm = (2048 - jj) & 2047;
        const unsigned short* pr = (const unsigned short*)w_r + 256 * c;
        const unsigned short* pi = (const unsigned short*)w_i + 256 * c;
        const float wr = 0.25f * (bf_lo(__ldg(pr + jj * 257)) + bf_lo(__ldg(pr + jm * 257)));
        const float wi = 0.25f * (bf_lo(__ldg(pi + jj * 257)) - bf_lo(__ldg(pi + jm * 257)));
        st_u2(ws->Wh + c * 2048 + jj, c ? pack_bf16(-wi, wr) : pack_bf16(wr, wi), tag);
        __syncwarp();
        hint_add_if(lane == 0, &ws->cntW[0]);
        mbar_wait(bars + 8 * B_XS, 0);
        const uint32_t t0 = (uint32_t)clock();
        uint4 v;
        do { v = ld_x4(ws->gate + rb * 128 + 4 * lane); spin_guard(t0); } while (__any_sync(0xffffffffu, ((v.x ^ tag) | (v.y ^ tag) | (v.z ^ tag) | (v.w ^ tag)) & 1));
        *(uint4*)(smem + OFF_G + lane * 16) = v;
        __syncwarp();
        mbar_arrive_if(lane < 4, bars + 8 * B_G);
      }
    auto part_load = [&](int i, unsigned ep1) {
      const uint32_t bytes = i < 2 ? U : U / 2;
      mbar_wait(bars + 8 * (B_PZ + (i == 0)), 0);
      mbar_expect_tx(bars + 8 * (B_HP + i), bytes);
      flag_wait(&ws->cntP[32 * (rb * 8 + j) + 8 * i], ep1 * (i < 2 ? 8u : 4u));
      bulk_load(sb + (i == 0 ? OFF_T : i == 1 ? 0 : i * (U / 2)), ws->part + (size_t)(rb * 8 + j) * 3072 + (i < 2 ? i * 1024 : 1024 + i * 512), bytes, bars + 8 * (B_HP + i));
      if (i == 2) PROF_EV(26);
    };
    if ((!helper || warp == 15) && elect_one()) {
      if (warp < 14) {
        const int p = warp - 12;
#pragma unroll 1
        for (int i = 4 + p; i < 14; i += 2) asm volatile("prefetch.tensormap [%0];" ::"l"((const char*)&maps + i * 128) : "memory");
#pragma unroll 1
        for (int n = 2; n < 31; n++) {
          const bool table = n == 4 || n >= 29;
          const bool half = n >= 17 && n < 21;
          const int q = n < 4 ? n : n < 17 ? n - 1 : n - 5;
          const CUtensorMap* m = table ? &maps.e : half ? &maps.g32 + p : &maps.g64 + p;
          const int c0 = table ? 0 : half ? f_half : f_full + 64 * (q >> 3);
          const int c1 = table ? (2 * rb + ((n & 1) ^ 1)) * 128 + 64 * p : half ? 128 * (n - 17) : 64 * (q & 7);
          const uint32_t fb = bars + 8 * (B_FA + (n & 3)), dst = sb + OFF_RING + (n & 3) * U + p * 8192;
          if (n < 4) mbar_wait(bars + 8 * (B_FE + n - 2), 0);
          else mbar_wait(bars + 8 * (B_EA + (n & 3)), ((n >> 2) & 1) ^ 1);
          tma2d(dst, m, fb, c0, c1);
          if (p == 0) mbar_expect_tx(fb, U);
        }
        part_load(2 + p, ld_x1(&ws->epoch[blockIdx.x * 8]) + 1);
      } else if (warp == 15) {
        const unsigned ep1 = ld_x1(&ws->epoch[blockIdx.x * 8]) + 1;
        flag_wait(&ws->cntX[helper ? 0 : 32 * j], ep1 * 16u);
        PROF_EV(22);
        mbar_expect_tx(bars + 8 * B_HX, U);
        bulk_load(sb + OFF_XB, ws->X + (size_t)(helper ? 128 : 16 * j + rb) * 8192, U, bars + 8 * B_HX);
        if (!helper) {
          flag_wait(&ws->cntT[32 * q4], ep1 * 128u);
          PROF_EV(23);
          mbar_expect_tx(bars + 8 * B_TL, U);
          tma3d(sb + OFF_T, &maps.t, bars + 8 * B_TL, 64 * j, 0, 2 * rb);
          part_load(0, ep1); part_load(1, ep1);
          mbar_wait(bars + 8 * (B_HP + 2), 0); mbar_wait(bars + 8 * (B_HP + 3), 0);
          ws->epoch[blockIdx.x * 8] = ep1;
        }
      } else {
#pragma unroll 1
        for (int q = 4; q < 8; q++) xf_load(q);
        mbar_wait(bars + 8 * (B_FE + 2), 0);
        mbar_expect_tx(bars + 8 * B_E0, U);
        tma2d(sb + OFF_XB, &maps.e, bars + 8 * B_E0, 0, 2 * rb * 128);
        tma2d(sb + OFF_XB + 8192, &maps.e, bars + 8 * B_E0, 0, 2 * rb * 128 + 64);
#pragma unroll 1
        for (int h2 = 0; h2 < 2; h2++) {
          const int s0 = 2 * rb + h2, sg = (s0 & ~6) | ((s0 & 2) << 1) | ((s0 & 4) >> 1);
          mbar_wait(bars + 8 * (B_XS + h2), 0);
#pragma unroll 1
          for (int c = 0; c < 2; c++) {
            asm volatile("cp.async.bulk.tensor.4d.global.shared::cta.bulk_group [%0, {%2, %3, %4, %5}], [%1];" ::"l"(&maps.xs),
                         "r"(sb + OFF_XB + h2 * 8192 + c * 4096), "r"(0), "r"(sg), "r"(0), "r"(16 * j + 8 * c) : "memory");
            if (j == 0)
              asm volatile("cp.async.bulk.global.shared::cta.bulk_group [%0], [%1], 256;" ::"l"(ws->X + 128 * 8192 + c * 4096 + sg * 128),
                           "r"(sb + OFF_SP + h2 * 512 + c * 256) : "memory");
            if (SPACE && h2 + c < 2) __nanosleep(SPACE);
          }
        }
        bulk_done_signal(&ws->cntX[32 * j]);
        PROF_EV(20);
#pragma unroll 1
        for (int t = 0; t < 8; t++) {
          const int col = 64 * (((q4 + 1 + (t >> 1)) & 3) + 4 * ((t & 1) ? rank : 1 - rank));
          const uint32_t fb = bars + 8 * (B_FT + (t & 3)), dst = sb + (t & 3) * TB;
          mbar_wait(bars + 8 * (B_ET + (t < 3 ? t + 1 : t & 3)), t >> 2);
          mbar_expect_tx(fb, (t & 1) ? 28672 : TB);
          tma2d(dst, &maps.d224, fb, col, 224 * j);
          if (!(t & 1)) tma3d(dst + 28672, &maps.fg, fb, col ^ 256, 16 * rank, 4 * q4);
        }
      }
    }
  }
}

typedef CUresult (*EncodeFn)(CUtensorMap*, CUtensorMapDataType, cuuint32_t, void*, const cuuint64_t*, const cuuint64_t*, const cuuint32_t*,
                             const cuuint32_t*, CUtensorMapInterleave, CUtensorMapSwizzle, CUtensorMapL2promotion, CUtensorMapFloatOOBfill);

static void encode(EncodeFn f, CUtensorMap* m, const void* base, int rank, const cuuint64_t* dims, const cuuint64_t* strides, const cuuint32_t* box,
                   CUtensorMapSwizzle sw) {
  cuuint32_t es[5] = {1, 1, 1, 1, 1};
  f(m, CU_TENSOR_MAP_DATA_TYPE_BFLOAT16, rank, (void*)base, dims, strides, box, es, CU_TENSOR_MAP_INTERLEAVE_NONE, sw,
    CU_TENSOR_MAP_L2_PROMOTION_L2_128B, CU_TENSOR_MAP_FLOAT_OOB_FILL_NONE);
}

extern "C" void kernel_launch(void* const* d_in, const int* in_sizes, int n_in, void* d_out, int out_size) {
  (void)in_sizes; (void)n_in; (void)out_size;
  const __nv_bfloat16* x = (const __nv_bfloat16*)d_in[0];
  const __nv_bfloat16* w_r = (const __nv_bfloat16*)d_in[1];
  const __nv_bfloat16* w_i = (const __nv_bfloat16*)d_in[2];
  const __nv_bfloat16* Wg = (const __nv_bfloat16*)d_in[4];
  const __nv_bfloat16* Wu = (const __nv_bfloat16*)d_in[5];
  const __nv_bfloat16* Wd = (const __nv_bfloat16*)d_in[6];
  const __nv_bfloat16* gw = (const __nv_bfloat16*)d_in[7];

  void* fp = nullptr; cudaDriverEntryPointQueryResult qr;
  cudaGetDriverEntryPoint("cuTensorMapEncodeTiled", &fp, cudaEnableDefault, &qr);
  EncodeFn enc = (EncodeFn)fp;
  void *pFT, *pET, *pDT, *pW;
  cudaGetSymbolAddress(&pDT, g_DT); cudaGetSymbolAddress(&pW, g_work);
  void *pX = ((Work*)pW)->X, *pT = ((Work*)pW)->T;
  cudaGetSymbolAddress(&pFT, g_FT); cudaGetSymbolAddress(&pET, g_ET);

  Maps mp;
  const CUtensorMapSwizzle S128 = CU_TENSOR_MAP_SWIZZLE_128B, S64 = CU_TENSOR_MAP_SWIZZLE_64B;
  { cuuint64_t d[3] = {512, 64, 32}, s[2] = {32768, 1024}; cuuint32_t b[3] = {64, 64, 2}; encode(enc, &mp.x, x, 3, d, s, b, S128); }
  { cuuint64_t d[2] = {512, 512}, s[1] = {1024}; cuuint32_t b[2] = {64, 64}; encode(enc, &mp.ft, pFT, 2, d, s, b, S128); }
  { cuuint64_t d[4] = {128, 32, 2, 129}, s[3] = {256, 8192, 16384}; cuuint32_t b[4] = {128, 1, 2, 8}; encode(enc, &mp.xs, pX, 4, d, s, b, CU_TENSOR_MAP_SWIZZLE_NONE); }
  { cuuint64_t d[4] = {64, 32, 8, 64}, s[3] = {65536, 128, 1024}; cuuint32_t b[4] = {32, 32, 2, 1}; encode(enc, &mp.ts, pT, 4, d, s, b, S64); }
  { cuuint64_t d[3] = {512, 32, 16}, s[2] = {1024, 32768}; cuuint32_t b[3] = {64, 16, 4}; encode(enc, &mp.fg, pFT, 3, d, s, b, S128); }
  { cuuint64_t d[3] = {512, 64, 32}, s[2] = {1024, 65536}; cuuint32_t b[3] = {64, 64, 2}; encode(enc, &mp.t, pT, 3, d, s, b, S128); }
  { cuuint64_t d[2] = {64, 4096}, s[1] = {128}; cuuint32_t b[2] = {64, 64}; encode(enc, &mp.e, pET, 2, d, s, b, S128); }
  { cuuint64_t d[2] = {1792, 512}, s[1] = {3584}; cuuint32_t b[2] = {64, 64}, b2[2] = {32, 128};
    encode(enc, &mp.g64, Wg, 2, d, s, b, S128); encode(enc, &mp.u64, Wu, 2, d, s, b, S128);
    encode(enc, &mp.g32, Wg, 2, d, s, b2, S64); encode(enc, &mp.u32, Wu, 2, d, s, b2, S64); }
  { cuuint64_t d[2] = {512, 1792}, s[1] = {1024}; cuuint32_t b[2] = {64, 224}; encode(enc, &mp.d224, Wd, 2, d, s, b, S128); }
  { cuuint64_t d[4] = {264, 32, 8, 8}, s[3] = {32896, 512, 4112}; cuuint32_t b[4] = {48, 32, 1, 1};
    encode(enc, &mp.wr, w_r, 4, d, s, b, CU_TENSOR_MAP_SWIZZLE_NONE); encode(enc, &mp.wi, w_i, 4, d, s, b, CU_TENSOR_MAP_SWIZZLE_NONE); }

  cudaFuncSetAttribute(fused_kernel, cudaFuncAttributeMaxDynamicSharedMemorySize, SMEM_BYTES);
  fused_kernel<<<NCTA, 512, SMEM_BYTES>>>((Work*)pW, (const uint16_t*)pDT, w_r, w_i, gw, x, (__nv_bfloat16*)d_out, mp);
}
```

```cpp
#include <cuda_runtime.h>
#include <cuda_bf16.h>
#include <cuda.h>
#include <stdint.h>

namespace tbl {
constexpr double PI = 3.14159265358979323846264338327950288;
constexpr double sin_s(double x) { double t = x, s = x; for (int n = 1; n < 12; n++) { t *= -x * x / ((2 * n) * (2 * n + 1)); s += t; } return s; }
constexpr double cos_s(double x) { double t = 1, s = 1; for (int n = 1; n < 12; n++) { t *= -x * x / ((2 * n - 1) * (2 * n)); s += t; } return s; }
constexpr double cos2048(int m) {
  m &= 2047; if (m > 1024) m = 2048 - m;
  bool neg = false; if (m > 512) { m = 1024 - m; neg = true; }
  double v = (m <= 256) ? cos_s(2 * PI * m / 2048) : sin_s(2 * PI * (512 - m) / 2048);
  return neg ? -v : v;
}
constexpr uint16_t to_bf16(double v) {
  if (v == 0) return 0;
  uint16_t s = 0; if (v < 0) { s = 0x8000; v = -v; }
  int e = 0; while (v >= 2) { v /= 2; e++; } while (v < 1) { v *= 2; e--; }
  double m = (v - 1) * 128; int mi = (int)m; double fr = m - mi;
  if (fr > 0.5 || (fr == 0.5 && (mi & 1))) mi++;
  if (mi == 128) { mi = 0; e++; }
  return (uint16_t)(s | ((e + 127) << 7) | mi);
}
struct CosT { uint16_t v[2048]; constexpr CosT() : v() { for (int i = 0; i < 2048; i++) v[i] = to_bf16(cos2048(i)); } };
struct alignas(1024) FT {
  uint16_t v[512 * 512];
  constexpr FT() : v() {
    CosT c;
    for (int r = 0; r < 512; r++) {
      int k = (r >> 5) * 16 + 2 * (r & 7) + ((r >> 4) & 1), e = (r >> 3) & 1;
      int mul = 4 * k, add = e ? 512 : 0;
      if (k == 0 && e == 1) { mul = 1024; add = 0; }
      for (int d = 0; d < 512; d++) v[r * 512 + d] = c.v[(d * mul + add) & 2047];
    }
  }
};
struct alignas(1024) ET {
  uint16_t v[2048 * 128];
  constexpr ET() : v() {
    CosT c;
    for (int s = 0; s < 2048; s++)
      for (int j = 0; j < 64; j++) {
        const int o = (s & 31) * 8192 + (s >> 5) * 64 + j;
        v[o] = c.v[(s * j) & 2047]; v[o + 4096] = c.v[(s * j + 512) & 2047];
      }
  }
};
struct alignas(1024) DT {
  uint16_t v[64 * 64];
  constexpr DT() : v() {
    CosT c;
    for (int r = 0; r < 64; r++)
      for (int n = 0; n < 64; n++) {
        const int sg = r >> 1, s0 = (sg & ~6) | ((sg & 2) << 1) | ((sg & 4) >> 1), e = r & 1, f = n & 1;
        const int m = 64 * s0 * (n >> 1) + (e == f ? 0 : e ? -512 : 512);
        v[r * 64 + (((n >> 3) ^ (r & 7)) << 3) + (n & 7)] = c.v[m & 2047];
      }
  }
};
}

__device__ constexpr tbl::FT g_FT = tbl::FT();
__device__ constexpr tbl::ET g_ET = tbl::ET();
__device__ constexpr tbl::DT g_DT = tbl::DT();

struct alignas(1024) Work {
  unsigned epoch[132 * 8];
  unsigned cntX[8 * 32], cntT[8 * 32], cntP[128 * 32], cntW[32], cntH[32];
  alignas(16) float gate[16 * 128];
  alignas(16) uint2 Wh[2 * 2048];
  alignas(16) uint2 Ts[32 * 64];
  alignas(1024) uint16_t X[129 * 8192];
  alignas(1024) uint16_t T[32 * 64 * 512];
  alignas(1024) uint4 part[128 * 3 * 1024];
};
__device__ Work g_work;
#define PROF_EV(i) do {} while (0)
#define PROF_CK(i) do {} while (0)

__device__ __forceinline__ uint32_t smem_u32(const void* p) { return (uint32_t)__cvta_generic_to_shared(p); }
__device__ __forceinline__ void mbar_init(uint32_t bar, uint32_t cnt) { asm volatile("mbarrier.init.shared::cta.b64 [%0], %1;" ::"r"(bar), "r"(cnt)); }
__device__ __forceinline__ void mbar_expect_tx(uint32_t bar, uint32_t bytes) { asm volatile("mbarrier.arrive.expect_tx.shared::cta.b64 _, [%0], %1;" ::"r"(bar), "r"(bytes) : "memory"); }
__device__ __forceinline__ void mbar_arrive(uint32_t bar) { asm volatile("mbarrier.arrive.shared::cta.b64 _, [%0];" ::"r"(bar) : "memory"); }
__device__ __forceinline__ bool elect_one() {
  uint32_t p;
  asm volatile("{\n.reg .pred p;\nelect.sync _|p, 0xffffffff;\nselp.u32 %0, 1, 0, p;\n}" : "=r"(p));
  return p;
}
__device__ __forceinline__ void mbar_arrive_if(bool p, uint32_t bar) {
  asm volatile("{\n.reg .pred p;\nsetp.ne.b32 p, %1, 0;\n@p mbarrier.arrive.shared::cta.b64 _, [%0];\n}" ::"r"(bar), "r"((int)p) : "memory");
}
__device__ __forceinline__ void hint_add_if(bool p, unsigned* a) {
  asm volatile("{\n.reg .pred p;\nsetp.ne.b32 p, %1, 0;\n@p red.relaxed.gpu.global.add.u32 [%0], 1;\n}" ::"l"(a), "r"((int)p) : "memory");
}
__device__ __forceinline__ bool mbar_try(uint32_t bar, uint32_t parity) {
  uint32_t ok;
  asm volatile("{\n.reg .pred p;\nmbarrier.test_wait.parity.shared::cta.b64 p, [%1], %2;\nselp.u32 %0, 1, 0, p;\n}" : "=r"(ok) : "r"(bar), "r"(parity) : "memory");
  return ok;
}
__device__ __forceinline__ void mbar_wait(uint32_t bar, uint32_t parity) {
  asm volatile(
      "{\n.reg .pred p;\n.reg .u32 n;\nmov.u32 n, 0;\n"
      "W_LOOP:\nmbarrier.try_wait.parity.shared::cta.b64 p, [%0], %1;\n@p bra W_DONE;\n"
      "add.u32 n, n, 1;\nsetp.lt.u32 p, n, 0x40000;\n@p bra W_LOOP;\ntrap;\nW_DONE:\n}" ::"r"(bar), "r"(parity) : "memory");
}
__device__ __forceinline__ void bulk_load(uint32_t dst, const void* src, uint32_t bytes, uint32_t bar) {
  asm volatile("cp.async.bulk.shared::cluster.global.mbarrier::complete_tx::bytes [%0], [%1], %2, [%3];" ::"r"(dst), "l"(src), "r"(bytes), "r"(bar) : "memory");
}
__device__ __forceinline__ void spin_guard(uint32_t t0) { if ((uint32_t)clock() - t0 > (1u << 30)) __trap(); }
__device__ __forceinline__ float2 ld_x2(const float2* p) { float2 v; asm volatile("ld.relaxed.gpu.global.v2.f32 {%0,%1}, [%2];" : "=f"(v.x), "=f"(v.y) : "l"(p) : "memory"); return v; }
__device__ __forceinline__ void st_u2(uint2* p, uint32_t a, uint32_t b) { asm volatile("st.relaxed.gpu.global.v2.u32 [%0], {%1,%2};" ::"l"(p), "r"(a), "r"(b) : "memory"); }
__device__ __forceinline__ uint32_t ld_x1(const void* p) { uint32_t v; asm volatile("ld.relaxed.gpu.global.u32 %0, [%1];" : "=r"(v) : "l"(p) : "memory"); return v; }
__device__ __forceinline__ uint4 ld_x4(const void* p) { uint4 v; asm volatile("ld.relaxed.gpu.global.v4.u32 {%0,%1,%2,%3}, [%4];" : "=r"(v.x), "=r"(v.y), "=r"(v.z), "=r"(v.w) : "l"(p) : "memory"); return v; }
__device__ __forceinline__ uint32_t mapa(uint32_t a, uint32_t cta) { uint32_t r; asm volatile("mapa.shared::cluster.u32 %0, %1, %2;" : "=r"(r) : "r"(a), "r"(cta)); return r; }
__device__ __forceinline__ void stsm4t(uint32_t a, uint32_t r0, uint32_t r1, uint32_t r2, uint32_t r3) {
  asm volatile("stmatrix.sync.aligned.m8n8.x4.trans.shared.b16 [%0], {%1,%2,%3,%4};" ::"r"(a), "r"(r0), "r"(r1), "r"(r2), "r"(r3) : "memory");
}
__device__ __forceinline__ void hint_add(unsigned* p) { asm volatile("red.relaxed.gpu.global.add.u32 [%0], 1;" ::"l"(p) : "memory"); }
__device__ __forceinline__ void hint_wait(const unsigned* p, unsigned target) {
  const uint32_t t0 = (uint32_t)clock();
  while ((int)(ld_x1(p) - target) < 0) spin_guard(t0);
}
__device__ __forceinline__ void bulk_done_signal(unsigned* p) {
  asm volatile("cp.async.bulk.commit_group;\ncp.async.bulk.wait_group 0;\nfence.proxy.async.global;" ::: "memory");
  hint_add(p);
}
__device__ __forceinline__ void flag_wait(const unsigned* p, unsigned target) {
  hint_wait(p, target);
  asm volatile("fence.proxy.async.global;" ::: "memory");
}
__device__ __forceinline__ void tma2d(uint32_t dst, const CUtensorMap* m, uint32_t bar, int c0, int c1) {
  asm volatile("cp.async.bulk.tensor.2d.shared::cluster.global.mbarrier::complete_tx::bytes [%0], [%1, {%3, %4}], [%2];" ::"r"(dst), "l"(m), "r"(bar), "r"(c0), "r"(c1) : "memory");
}
__device__ __forceinline__ void tma3d(uint32_t dst, const CUtensorMap* m, uint32_t bar, int c0, int c1, int c2) {
  asm volatile("cp.async.bulk.tensor.3d.shared::cluster.global.mbarrier::complete_tx::bytes [%0], [%1, {%3, %4, %5}], [%2];" ::"r"(dst), "l"(m), "r"(bar), "r"(c0), "r"(c1), "r"(c2) : "memory");
}
__device__ __forceinline__ void tma4d(uint32_t dst, const CUtensorMap* m, uint32_t bar, int c0, int c1, int c2, int c3) {
  asm volatile("cp.async.bulk.tensor.4d.shared::cluster.global.mbarrier::complete_tx::bytes [%0], [%1, {%3, %4, %5, %6}], [%2];" ::"r"(dst), "l"(m), "r"(bar), "r"(c0), "r"(c1), "r"(c2), "r"(c3) : "memory");
}
__device__ __forceinline__ void wg_fence() { asm volatile("wgmma.fence.sync.aligned;" ::: "memory"); }
__device__ __forceinline__ void wg_commit() { asm volatile("wgmma.commit_group.sync.aligned;" ::: "memory"); }
template <int N> __device__ __forceinline__ void wg_wait() { asm volatile("wgmma.wait_group.sync.aligned %0;" ::"n"(N) : "memory"); }
template <int O, int N, int NN> __device__ __forceinline__ void fence_regs(float (&d)[NN]) {
#pragma unroll
  for (int i = 0; i < N; i++) asm volatile("" : "+f"(d[O + i])::"memory");
}
__device__ __forceinline__ uint32_t pack_bf16(float lo, float hi) {
  uint32_t r; asm("cvt.rn.bf16x2.f32 %0, %1, %2;" : "=r"(r) : "f"(hi), "f"(lo)); return r;
}
__device__ __forceinline__ uint32_t pack_pin(float lo, float hi) {
  uint32_t r; asm volatile("cvt.rn.bf16x2.f32 %0, %1, %2;" : "=r"(r) : "f"(hi), "f"(lo) : "memory"); return r;
}
__device__ __forceinline__ uint32_t add_bf2(uint32_t a, uint32_t b) { uint32_t r; asm("add.rn.bf16x2 %0, %1, %2;" : "=r"(r) : "r"(a), "r"(b)); return r; }
__device__ __forceinline__ float bf_lo(uint32_t u) { return __uint_as_float(u << 16); }
__device__ __forceinline__ float bf_hi(uint32_t u) { return __uint_as_float(u & 0xffff0000u); }

__device__ __forceinline__ uint64_t d128(uint32_t lo) { uint64_t d; asm("mov.b64 %0, {%1, 0x40000040};" : "=l"(d) : "r"(lo)); return d; }
__device__ __forceinline__ uint64_t d64(uint32_t lo) { uint64_t d; asm("mov.b64 %0, {%1, 0x80000020};" : "=l"(d) : "r"(lo)); return d; }
template<int O,int TB,int ACC,int NN> __device__ __forceinline__ void mma_ss64(float (&d)[NN], uint64_t da, uint64_t db, int sd = 0){
  if constexpr (ACC == 1) asm volatile("wgmma.mma_async.sync.aligned.m64n64k16.f32.bf16.bf16 {%0,%1,%2,%3,%4,%5,%6,%7,%8,%9,%10,%11,%12,%13,%14,%15,%16,%17,%18,%19,%20,%21,%22,%23,%24,%25,%26,%27,%28,%29,%30,%31}, %32, %33, 1, 1, 1, %35, %34;"
   : "+f"(d[O+0]), "+f"(d[O+1]), "+f"(d[O+2]), "+f"(d[O+3]), "+f"(d[O+4]), "+f"(d[O+5]), "+f"(d[O+6]), "+f"(d[O+7]), "+f"(d[O+8]), "+f"(d[O+9]), "+f"(d[O+10]), "+f"(d[O+11]), "+f"(d[O+12]), "+f"(d[O+13]), "+f"(d[O+14]), "+f"(d[O+15]), "+f"(d[O+16]), "+f"(d[O+17]), "+f"(d[O+18]), "+f"(d[O+19]), "+f"(d[O+20]), "+f"(d[O+21]), "+f"(d[O+22]), "+f"(d[O+23]), "+f"(d[O+24]), "+f"(d[O+25]), "+f"(d[O+26]), "+f"(d[O+27]), "+f"(d[O+28]), "+f"(d[O+29]), "+f"(d[O+30]), "+f"(d[O+31])
   : "l"(da), "l"(db), "n"(TB & 1), "n"(TB >> 1));
  else if constexpr (ACC == 0) asm volatile("wgmma.mma_async.sync.aligned.m64n64k16.f32.bf16.bf16 {%0,%1,%2,%3,%4,%5,%6,%7,%8,%9,%10,%11,%12,%13,%14,%15,%16,%17,%18,%19,%20,%21,%22,%23,%24,%25,%26,%27,%28,%29,%30,%31}, %32, %33, 0, 1, 1, %35, %34;"
   : "=f"(d[O+0]), "=f"(d[O+1]), "=f"(d[O+2]), "=f"(d[O+3]), "=f"(d[O+4]), "=f"(d[O+5]), "=f"(d[O+6]), "=f"(d[O+7]), "=f"(d[O+8]), "=f"(d[O+9]), "=f"(d[O+10]), "=f"(d[O+11]), "=f"(d[O+12]), "=f"(d[O+13]), "=f"(d[O+14]), "=f"(d[O+15]), "=f"(d[O+16]), "=f"(d[O+17]), "=f"(d[O+18]), "=f"(d[O+19]), "=f"(d[O+20]), "=f"(d[O+21]), "=f"(d[O+22]), "=f"(d[O+23]), "=f"(d[O+24]), "=f"(d[O+25]), "=f"(d[O+26]), "=f"(d[O+27]), "=f"(d[O+28]), "=f"(d[O+29]), "=f"(d[O+30]), "=f"(d[O+31])
   : "l"(da), "l"(db), "n"(TB & 1), "n"(TB >> 1));
  else asm volatile("{\n.reg .pred p;\nsetp.ne.b32 p, %36, 0;\nwgmma.mma_async.sync.aligned.m64n64k16.f32.bf16.bf16 {%0,%1,%2,%3,%4,%5,%6,%7,%8,%9,%10,%11,%12,%13,%14,%15,%16,%17,%18,%19,%20,%21,%22,%23,%24,%25,%26,%27,%28,%29,%30,%31}, %32, %33, p, 1, 1, %35, %34;\n}"
   : "+f"(d[O+0]), "+f"(d[O+1]), "+f"(d[O+2]), "+f"(d[O+3]), "+f"(d[O+4]), "+f"(d[O+5]), "+f"(d[O+6]), "+f"(d[O+7]), "+f"(d[O+8]), "+f"(d[O+9]), "+f"(d[O+10]), "+f"(d[O+11]), "+f"(d[O+12]), "+f"(d[O+13]), "+f"(d[O+14]), "+f"(d[O+15]), "+f"(d[O+16]), "+f"(d[O+17]), "+f"(d[O+18]), "+f"(d[O+19]), "+f"(d[O+20]), "+f"(d[O+21]), "+f"(d[O+22]), "+f"(d[O+23]), "+f"(d[O+24]), "+f"(d[O+25]), "+f"(d[O+26]), "+f"(d[O+27]), "+f"(d[O+28]), "+f"(d[O+29]), "+f"(d[O+30]), "+f"(d[O+31])
   : "l"(da), "l"(db), "n"(TB & 1), "n"(TB >> 1), "r"(sd));
}
template<int O,int TB,int ACC,int NN> __device__ __forceinline__ void mma_rs64(float (&d)[NN], uint32_t a0, uint32_t a1, uint32_t a2, uint32_t a3, uint64_t db, int sd = 0){
  if constexpr (ACC == 1) asm volatile("wgmma.mma_async.sync.aligned.m64n64k16.f32.bf16.bf16 {%0,%1,%2,%3,%4,%5,%6,%7,%8,%9,%10,%11,%12,%13,%14,%15,%16,%17,%18,%19,%20,%21,%22,%23,%24,%25,%26,%27,%28,%29,%30,%31}, {%32,%33,%34,%35}, %36, 1, 1, 1, %37;"
   : "+f"(d[O+0]), "+f"(d[O+1]), "+f"(d[O+2]), "+f"(d[O+3]), "+f"(d[O+4]), "+f"(d[O+5]), "+f"(d[O+6]), "+f"(d[O+7]), "+f"(d[O+8]), "+f"(d[O+9]), "+f"(d[O+10]), "+f"(d[O+11]), "+f"(d[O+12]), "+f"(d[O+13]), "+f"(d[O+14]), "+f"(d[O+15]), "+f"(d[O+16]), "+f"(d[O+17]), "+f"(d[O+18]), "+f"(d[O+19]), "+f"(d[O+20]), "+f"(d[O+21]), "+f"(d[O+22]), "+f"(d[O+23]), "+f"(d[O+24]), "+f"(d[O+25]), "+f"(d[O+26]), "+f"(d[O+27]), "+f"(d[O+28]), "+f"(d[O+29]), "+f"(d[O+30]), "+f"(d[O+31])
   : "r"(a0), "r"(a1), "r"(a2), "r"(a3), "l"(db), "n"(TB));
  else if constexpr (ACC == 0) asm volatile("wgmma.mma_async.sync.aligned.m64n64k16.f32.bf16.bf16 {%0,%1,%2,%3,%4,%5,%6,%7,%8,%9,%10,%11,%12,%13,%14,%15,%16,%17,%18,%19,%20,%21,%22,%23,%24,%25,%26,%27,%28,%29,%30,%31}, {%32,%33,%34,%35}, %36, 0, 1, 1, %37;"
   : "=f"(d[O+0]), "=f"(d[O+1]), "=f"(d[O+2]), "=f"(d[O+3]), "=f"(d[O+4]), "=f"(d[O+5]), "=f"(d[O+6]), "=f"(d[O+7]), "=f"(d[O+8]), "=f"(d[O+9]), "=f"(d[O+10]), "=f"(d[O+11]), "=f"(d[O+12]), "=f"(d[O+13]), "=f"(d[O+14]), "=f"(d[O+15]), "=f"(d[O+16]), "=f"(d[O+17]), "=f"(d[O+18]), "=f"(d[O+19]), "=f"(d[O+20]), "=f"(d[O+21]), "=f"(d[O+22]), "=f"(d[O+23]), "=f"(d[O+24]), "=f"(d[O+25]), "=f"(d[O+26]), "=f"(d[O+27]), "=f"(d[O+28]), "=f"(d[O+29]), "=f"(d[O+30]), "=f"(d[O+31])
   : "r"(a0), "r"(a1), "r"(a2), "r"(a3), "l"(db), "n"(TB));
  else asm volatile("{\n.reg .pred p;\nsetp.ne.b32 p, %38, 0;\nwgmma.mma_async.sync.aligned.m64n64k16.f32.bf16.bf16 {%0,%1,%2,%3,%4,%5,%6,%7,%8,%9,%10,%11,%12,%13,%14,%15,%16,%17,%18,%19,%20,%21,%22,%23,%24,%25,%26,%27,%28,%29,%30,%31}, {%32,%33,%34,%35}, %36, p, 1, 1, %37;\n}"
   : "+f"(d[O+0]), "+f"(d[O+1]), "+f"(d[O+2]), "+f"(d[O+3]), "+f"(d[O+4]), "+f"(d[O+5]), "+f"(d[O+6]), "+f"(d[O+7]), "+f"(d[O+8]), "+f"(d[O+9]), "+f"(d[O+10]), "+f"(d[O+11]), "+f"(d[O+12]), "+f"(d[O+13]), "+f"(d[O+14]), "+f"(d[O+15]), "+f"(d[O+16]), "+f"(d[O+17]), "+f"(d[O+18]), "+f"(d[O+19]), "+f"(d[O+20]), "+f"(d[O+21]), "+f"(d[O+22]), "+f"(d[O+23]), "+f"(d[O+24]), "+f"(d[O+25]), "+f"(d[O+26]), "+f"(d[O+27]), "+f"(d[O+28]), "+f"(d[O+29]), "+f"(d[O+30]), "+f"(d[O+31])
   : "r"(a0), "r"(a1), "r"(a2), "r"(a3), "l"(db), "n"(TB), "r"(sd));
}
template<int O,int TB,int ACC,int NN> __device__ __forceinline__ void mma_ss128(float (&d)[NN], uint64_t da, uint64_t db, int sd = 0){
  if constexpr (ACC == 1) asm volatile("wgmma.mma_async.sync.aligned.m64n128k16.f32.bf16.bf16 {%0,%1,%2,%3,%4,%5,%6,%7,%8,%9,%10,%11,%12,%13,%14,%15,%16,%17,%18,%19,%20,%21,%22,%23,%24,%25,%26,%27,%28,%29,%30,%31,%32,%33,%34,%35,%36,%37,%38,%39,%40,%41,%42,%43,%44,%45,%46,%47,%48,%49,%50,%51,%52,%53,%54,%55,%56,%57,%58,%59,%60,%61,%62,%63}, %64, %65, 1, 1, 1, %67, %66;"
   : "+f"(d[O+0]), "+f"(d[O+1]), "+f"(d[O+2]), "+f"(d[O+3]), "+f"(d[O+4]), "+f"(d[O+5]), "+f"(d[O+6]), "+f"(d[O+7]), "+f"(d[O+8]), "+f"(d[O+9]), "+f"(d[O+10]), "+f"(d[O+11]), "+f"(d[O+12]), "+f"(d[O+13]), "+f"(d[O+14]), "+f"(d[O+15]), "+f"(d[O+16]), "+f"(d[O+17]), "+f"(d[O+18]), "+f"(d[O+19]), "+f"(d[O+20]), "+f"(d[O+21]), "+f"(d[O+22]), "+f"(d[O+23]), "+f"(d[O+24]), "+f"(d[O+25]), "+f"(d[O+26]), "+f"(d[O+27]), "+f"(d[O+28]), "+f"(d[O+29]), "+f"(d[O+30]), "+f"(d[O+31]), "+f"(d[O+32]), "+f"(d[O+33]), "+f"(d[O+34]), "+f"(d[O+35]), "+f"(d[O+36]), "+f"(d[O+37]), "+f"(d[O+38]), "+f"(d[O+39]), "+f"(d[O+40]), "+f"(d[O+41]), "+f"(d[O+42]), "+f"(d[O+43]), "+f"(d[O+44]), "+f"(d[O+45]), "+f"(d[O+46]), "+f"(d[O+47]), "+f"(d[O+48]), "+f"(d[O+49]), "+f"(d[O+50]), "+f"(d[O+51]), "+f"(d[O+52]), "+f"(d[O+53]), "+f"(d[O+54]), "+f"(d[O+55]), "+f"(d[O+56]), "+f"(d[O+57]), "+f"(d[O+58]), "+f"(d[O+59]), "+f"(d[O+60]), "+f"(d[O+61]), "+f"(d[O+62]), "+f"(d[O+63])
   : "l"(da), "l"(db), "n"(TB & 1), "n"(TB >> 1));
  else if constexpr (ACC == 0) asm volatile("wgmma.mma_async.sync.aligned.m64n128k16.f32.bf16.bf16 {%0,%1,%2,%3,%4,%5,%6,%7,%8,%9,%10,%11,%12,%13,%14,%15,%16,%17,%18,%19,%20,%21,%22,%23,%24,%25,%26,%27,%28,%29,%30,%31,%32,%33,%34,%35,%36,%37,%38,%39,%40,%41,%42,%43,%44,%45,%46,%47,%48,%49,%50,%51,%52,%53,%54,%55,%56,%57,%58,%59,%60,%61,%62,%63}, %64, %65, 0, 1, 1, %67, %66;"
   : "=f"(d[O+0]), "=f"(d[O+1]), "=f"(d[O+2]), "=f"(d[O+3]), "=f"(d[O+4]), "=f"(d[O+5]), "=f"(d[O+6]), "=f"(d[O+7]), "=f"(d[O+8]), "=f"(d[O+9]), "=f"(d[O+10]), "=f"(d[O+11]), "=f"(d[O+12]), "=f"(d[O+13]), "=f"(d[O+14]), "=f"(d[O+15]), "=f"(d[O+16]), "=f"(d[O+17]), "=f"(d[O+18]), "=f"(d[O+19]), "=f"(d[O+20]), "=f"(d[O+21]), "=f"(d[O+22]), "=f"(d[O+23]), "=f"(d[O+24]), "=f"(d[O+25]), "=f"(d[O+26]), "=f"(d[O+27]), "=f"(d[O+28]), "=f"(d[O+29]), "=f"(d[O+30]), "=f"(d[O+31]), "=f"(d[O+32]), "=f"(d[O+33]), "=f"(d[O+34]), "=f"(d[O+35]), "=f"(d[O+36]), "=f"(d[O+37]), "=f"(d[O+38]), "=f"(d[O+39]), "=f"(d[O+40]), "=f"(d[O+41]), "=f"(d[O+42]), "=f"(d[O+43]), "=f"(d[O+44]), "=f"(d[O+45]), "=f"(d[O+46]), "=f"(d[O+47]), "=f"(d[O+48]), "=f"(d[O+49]), "=f"(d[O+50]), "=f"(d[O+51]), "=f"(d[O+52]), "=f"(d[O+53]), "=f"(d[O+54]), "=f"(d[O+55]), "=f"(d[O+56]), "=f"(d[O+57]), "=f"(d[O+58]), "=f"(d[O+59]), "=f"(d[O+60]), "=f"(d[O+61]), "=f"(d[O+62]), "=f"(d[O+63])
   : "l"(da), "l"(db), "n"(TB & 1), "n"(TB >> 1));
  else asm volatile("{\n.reg .pred p;\nsetp.ne.b32 p, %68, 0;\nwgmma.mma_async.sync.aligned.m64n128k16.f32.bf16.bf16 {%0,%1,%2,%3,%4,%5,%6,%7,%8,%9,%10,%11,%12,%13,%14,%15,%16,%17,%18,%19,%20,%21,%22,%23,%24,%25,%26,%27,%28,%29,%30,%31,%32,%33,%34,%35,%36,%37,%38,%39,%40,%41,%42,%43,%44,%45,%46,%47,%48,%49,%50,%51,%52,%53,%54,%55,%56,%57,%58,%59,%60,%61,%62,%63}, %64, %65, p, 1, 1, %67, %66;\n}"
   : "+f"(d[O+0]), "+f"(d[O+1]), "+f"(d[O+2]), "+f"(d[O+3]), "+f"(d[O+4]), "+f"(d[O+5]), "+f"(d[O+6]), "+f"(d[O+7]), "+f"(d[O+8]), "+f"(d[O+9]), "+f"(d[O+10]), "+f"(d[O+11]), "+f"(d[O+12]), "+f"(d[O+13]), "+f"(d[O+14]), "+f"(d[O+15]), "+f"(d[O+16]), "+f"(d[O+17]), "+f"(d[O+18]), "+f"(d[O+19]), "+f"(d[O+20]), "+f"(d[O+21]), "+f"(d[O+22]), "+f"(d[O+23]), "+f"(d[O+24]), "+f"(d[O+25]), "+f"(d[O+26]), "+f"(d[O+27]), "+f"(d[O+28]), "+f"(d[O+29]), "+f"(d[O+30]), "+f"(d[O+31]), "+f"(d[O+32]), "+f"(d[O+33]), "+f"(d[O+34]), "+f"(d[O+35]), "+f"(d[O+36]), "+f"(d[O+37]), "+f"(d[O+38]), "+f"(d[O+39]), "+f"(d[O+40]), "+f"(d[O+41]), "+f"(d[O+42]), "+f"(d[O+43]), "+f"(d[O+44]), "+f"(d[O+45]), "+f"(d[O+46]), "+f"(d[O+47]), "+f"(d[O+48]), "+f"(d[O+49]), "+f"(d[O+50]), "+f"(d[O+51]), "+f"(d[O+52]), "+f"(d[O+53]), "+f"(d[O+54]), "+f"(d[O+55]), "+f"(d[O+56]), "+f"(d[O+57]), "+f"(d[O+58]), "+f"(d[O+59]), "+f"(d[O+60]), "+f"(d[O+61]), "+f"(d[O+62]), "+f"(d[O+63])
   : "l"(da), "l"(db), "n"(TB & 1), "n"(TB >> 1), "r"(sd));
}
template<int O,int TB,int ACC,int NN> __device__ __forceinline__ void mma_rs128(float (&d)[NN], uint32_t a0, uint32_t a1, uint32_t a2, uint32_t a3, uint64_t db, int sd = 0){
  if constexpr (ACC == 1) asm volatile("wgmma.mma_async.sync.aligned.m64n128k16.f32.bf16.bf16 {%0,%1,%2,%3,%4,%5,%6,%7,%8,%9,%10,%11,%12,%13,%14,%15,%16,%17,%18,%19,%20,%21,%22,%23,%24,%25,%26,%27,%28,%29,%30,%31,%32,%33,%34,%35,%36,%37,%38,%39,%40,%41,%42,%43,%44,%45,%46,%47,%48,%49,%50,%51,%52,%53,%54,%55,%56,%57,%58,%59,%60,%61,%62,%63}, {%64,%65,%66,%67}, %68, 1, 1, 1, %69;"
   : "+f"(d[O+0]), "+f"(d[O+1]), "+f"(d[O+2]), "+f"(d[O+3]), "+f"(d[O+4]), "+f"(d[O+5]), "+f"(d[O+6]), "+f"(d[O+7]), "+f"(d[O+8]), "+f"(d[O+9]), "+f"(d[O+10]), "+f"(d[O+11]), "+f"(d[O+12]), "+f"(d[O+13]), "+f"(d[O+14]), "+f"(d[O+15]), "+f"(d[O+16]), "+f"(d[O+17]), "+f"(d[O+18]), "+f"(d[O+19]), "+f"(d[O+20]), "+f"(d[O+21]), "+f"(d[O+22]), "+f"(d[O+23]), "+f"(d[O+24]), "+f"(d[O+25]), "+f"(d[O+26]), "+f"(d[O+27]), "+f"(d[O+28]), "+f"(d[O+29]), "+f"(d[O+30]), "+f"(d[O+31]), "+f"(d[O+32]), "+f"(d[O+33]), "+f"(d[O+34]), "+f"(d[O+35]), "+f"(d[O+36]), "+f"(d[O+37]), "+f"(d[O+38]), "+f"(d[O+39]), "+f"(d[O+40]), "+f"(d[O+41]), "+f"(d[O+42]), "+f"(d[O+43]), "+f"(d[O+44]), "+f"(d[O+45]), "+f"(d[O+46]), "+f"(d[O+47]), "+f"(d[O+48]), "+f"(d[O+49]), "+f"(d[O+50]), "+f"(d[O+51]), "+f"(d[O+52]), "+f"(d[O+53]), "+f"(d[O+54]), "+f"(d[O+55]), "+f"(d[O+56]), "+f"(d[O+57]), "+f"(d[O+58]), "+f"(d[O+59]), "+f"(d[O+60]), "+f"(d[O+61]), "+f"(d[O+62]), "+f"(d[O+63])
   : "r"(a0), "r"(a1), "r"(a2), "r"(a3), "l"(db), "n"(TB));
  else if constexpr (ACC == 0) asm volatile("wgmma.mma_async.sync.aligned.m64n128k16.f32.bf16.bf16 {%0,%1,%2,%3,%4,%5,%6,%7,%8,%9,%10,%11,%12,%13,%14,%15,%16,%17,%18,%19,%20,%21,%22,%23,%24,%25,%26,%27,%28,%29,%30,%31,%32,%33,%34,%35,%36,%37,%38,%39,%40,%41,%42,%43,%44,%45,%46,%47,%48,%49,%50,%51,%52,%53,%54,%55,%56,%57,%58,%59,%60,%61,%62,%63}, {%64,%65,%66,%67}, %68, 0, 1, 1, %69;"
   : "=f"(d[O+0]), "=f"(d[O+1]), "=f"(d[O+2]), "=f"(d[O+3]), "=f"(d[O+4]), "=f"(d[O+5]), "=f"(d[O+6]), "=f"(d[O+7]), "=f"(d[O+8]), "=f"(d[O+9]), "=f"(d[O+10]), "=f"(d[O+11]), "=f"(d[O+12]), "=f"(d[O+13]), "=f"(d[O+14]), "=f"(d[O+15]), "=f"(d[O+16]), "=f"(d[O+17]), "=f"(d[O+18]), "=f"(d[O+19]), "=f"(d[O+20]), "=f"(d[O+21]), "=f"(d[O+22]), "=f"(d[O+23]), "=f"(d[O+24]), "=f"(d[O+25]), "=f"(d[O+26]), "=f"(d[O+27]), "=f"(d[O+28]), "=f"(d[O+29]), "=f"(d[O+30]), "=f"(d[O+31]), "=f"(d[O+32]), "=f"(d[O+33]), "=f"(d[O+34]), "=f"(d[O+35]), "=f"(d[O+36]), "=f"(d[O+37]), "=f"(d[O+38]), "=f"(d[O+39]), "=f"(d[O+40]), "=f"(d[O+41]), "=f"(d[O+42]), "=f"(d[O+43]), "=f"(d[O+44]), "=f"(d[O+45]), "=f"(d[O+46]), "=f"(d[O+47]), "=f"(d[O+48]), "=f"(d[O+49]), "=f"(d[O+50]), "=f"(d[O+51]), "=f"(d[O+52]), "=f"(d[O+53]), "=f"(d[O+54]), "=f"(d[O+55]), "=f"(d[O+56]), "=f"(d[O+57]), "=f"(d[O+58]), "=f"(d[O+59]), "=f"(d[O+60]), "=f"(d[O+61]), "=f"(d[O+62]), "=f"(d[O+63])
   : "r"(a0), "r"(a1), "r"(a2), "r"(a3), "l"(db), "n"(TB));
  else asm volatile("{\n.reg .pred p;\nsetp.ne.b32 p, %70, 0;\nwgmma.mma_async.sync.aligned.m64n128k16.f32.bf16.bf16 {%0,%1,%2,%3,%4,%5,%6,%7,%8,%9,%10,%11,%12,%13,%14,%15,%16,%17,%18,%19,%20,%21,%22,%23,%24,%25,%26,%27,%28,%29,%30,%31,%32,%33,%34,%35,%36,%37,%38,%39,%40,%41,%42,%43,%44,%45,%46,%47,%48,%49,%50,%51,%52,%53,%54,%55,%56,%57,%58,%59,%60,%61,%62,%63}, {%64,%65,%66,%67}, %68, p, 1, 1, %69;\n}"
   : "+f"(d[O+0]), "+f"(d[O+1]), "+f"(d[O+2]), "+f"(d[O+3]), "+f"(d[O+4]), "+f"(d[O+5]), "+f"(d[O+6]), "+f"(d[O+7]), "+f"(d[O+8]), "+f"(d[O+9]), "+f"(d[O+10]), "+f"(d[O+11]), "+f"(d[O+12]), "+f"(d[O+13]), "+f"(d[O+14]), "+f"(d[O+15]), "+f"(d[O+16]), "+f"(d[O+17]), "+f"(d[O+18]), "+f"(d[O+19]), "+f"(d[O+20]), "+f"(d[O+21]), "+f"(d[O+22]), "+f"(d[O+23]), "+f"(d[O+24]), "+f"(d[O+25]), "+f"(d[O+26]), "+f"(d[O+27]), "+f"(d[O+28]), "+f"(d[O+29]), "+f"(d[O+30]), "+f"(d[O+31]), "+f"(d[O+32]), "+f"(d[O+33]), "+f"(d[O+34]), "+f"(d[O+35]), "+f"(d[O+36]), "+f"(d[O+37]), "+f"(d[O+38]), "+f"(d[O+39]), "+f"(d[O+40]), "+f"(d[O+41]), "+f"(d[O+42]), "+f"(d[O+43]), "+f"(d[O+44]), "+f"(d[O+45]), "+f"(d[O+46]), "+f"(d[O+47]), "+f"(d[O+48]), "+f"(d[O+49]), "+f"(d[O+50]), "+f"(d[O+51]), "+f"(d[O+52]), "+f"(d[O+53]), "+f"(d[O+54]), "+f"(d[O+55]), "+f"(d[O+56]), "+f"(d[O+57]), "+f"(d[O+58]), "+f"(d[O+59]), "+f"(d[O+60]), "+f"(d[O+61]), "+f"(d[O+62]), "+f"(d[O+63])
   : "r"(a0), "r"(a1), "r"(a2), "r"(a3), "l"(db), "n"(TB), "r"(sd));
}

#define NEARLY 0
#define XAHEAD 3
#define HEADN 6
#define WBATCH 1
#define WB 8
#define WSLEEP 20
#define XSPREAD 4
#define NOSEND 0
#define MSPLIT 2
#define PFALL 1
#define L2PF 0
#define STAG 1
#define EPF 2
#define XNB 2
#define FNB 0
#define GNB 0
#define TH 4
#define PF0 4
#define FSPLIT 1
#define MGLU 1
#define SPC 2
#define TL 14
#define GKB 4
#define T0A 6
#define T0B 10
#define TGATE 1
#define ZLATE 0
#define EARLYADD 0
#define OA 4
#define OB 11
#define EB 9
#define SPACE 100
#define WPF 1
#define WAFTER 7
#define WPACE 0
#define GATE_AT 4
#define TPACE 40
#define PFMODE 0
#define MAPMODE 1
template <int V> struct IC { static constexpr int value = V; };
struct Maps { CUtensorMap x, ft, g64, u64, e, wr, wi, xs, ts, t, g32, u32, d224, fg; };

constexpr int NCTA = 130;
constexpr int U = 16384;
constexpr int TB = 36864;
constexpr int OFF_RING = 8 * U, OFF_Z = 12 * U, OFF_XB = 12 * U, OFF_T = 13 * U, OFF_D = OFF_T;
constexpr int OFF_BAR = 14 * U, OFF_SP = OFF_BAR + 512, OFF_G = OFF_SP + 1024 + 128;
constexpr int SMEM_BYTES = OFF_G + 512;
constexpr int B_FX = 0, B_FA = 8, B_FT = 12, B_Z = 16, B_W = 24, B_HX = 25, B_TL = 26, B_HP = 27, B_WR = 31, B_E0 = 35;
constexpr int B_EA = 36, B_ET = 40, B_PZ = 44, B_RDY = 46, B_FE = 47;
constexpr int B_T = 51, B_XS = 52, B_G = 54, B_RD0 = 55, NBAR = 56;
__host__ __device__ constexpr int rslot(int n) { return n & 3; }
__host__ __device__ constexpr int rpar(int n) { return (n >> 2) & 1; }

__global__ void __cluster_dims__(2, 1, 1) __launch_bounds__(512, 1)
fused_kernel(Work* __restrict__ ws, const uint16_t* __restrict__ dtab, const __nv_bfloat16* __restrict__ w_r, const __nv_bfloat16* __restrict__ w_i,
             const __nv_bfloat16* __restrict__ gate_w, const __nv_bfloat16* __restrict__ x, __nv_bfloat16* __restrict__ out,
             const __grid_constant__ Maps maps) {
  extern __shared__ __align__(1024) uint8_t smem[];
  if (threadIdx.x < 32 && elect_one()) {
#pragma unroll
    for (int i = 0; i < PF0; i++) asm volatile("prefetch.tensormap [%0];" ::"l"((const char*)&maps + i * 128) : "memory");
  }
  const uint32_t sb = smem_u32(smem);
  const uint32_t bars = sb + OFF_BAR;
  const int tid = threadIdx.x, lane = tid & 31;
  const int warp = __shfl_sync(0xffffffffu, tid >> 5, 0);
  const bool helper = blockIdx.x >= 128;
  const int cl = (blockIdx.x >> 1) & 63, rank = blockIdx.x & 1;
  const int q4 = (cl & 1) | ((cl >> 2) & 2), rb = ((cl >> 1) & 3) | ((cl >> 4) << 2);
  const int j = 2 * q4 + rank;
  const int f_full = 448 * q4 + (rank ? 256 : 0);
  const int f_half = 448 * q4 + (rank ? 224 : 192);

  if (tid == 64) { PROF_EV(0); PROF_CK(40); }
  if (warp < 8) {
    if (!helper && tid < 32) {
      const int r = 16 * j + (tid & 15);
      asm volatile("prefetch.global.L2 [%0];" ::"l"(x + (size_t)(2 * rb + (r >> 6) + 32 * (r & 63)) * 512 + 64 * (tid >> 4)));
    }
    asm volatile("barrier.cluster.arrive.relaxed.aligned;" ::: "memory");
    asm volatile("setmaxnreg.inc.sync.aligned.u32 192;");
    if (!helper) {
      const int wg = warp >> 2, w = warp & 3, g = lane >> 2;
      const bool elect = (tid & 127) == 0;
      float cX[32], cA[64], cB[64], cC[64], ci[64], ct[64];
      const int zero = blockIdx.x >> 16;
      uint32_t h[56], yf[16];
      const uint32_t d0 = (sb & 0x3FFFF) >> 4;
      const uint32_t dK = d0 | (1u << 16), dN = d0 | (512u << 16);
      const uint32_t dX = dK + wg * 512;
      constexpr uint32_t RING = OFF_RING >> 4;
      auto waitA = [&](int n) { mbar_wait(bars + 8 * (B_FA + rslot(n)), rpar(n)); };
      auto freeA = [&](int n) { mbar_arrive_if(elect, bars + 8 * (B_EA + rslot(n))); };
      auto nop = [] {};

      asm volatile("bar.sync 0, 384;" ::: "memory");
#pragma unroll 1
      for (int i = 0; i < 4; i++) {
        const uint64_t dx = d128(dX + i * 2048), df = d128(dK + (OFF_XB >> 4) + (i & 1) * 1024);
        mbar_wait(bars + 8 * (B_FX + 2 * i), 0);
        wg_fence();
        mma_ss64<0, 0, 2>(cX, df, dx, i);
        mma_ss64<0, 0, 1>(cX, df + 2, dx + 2);
        wg_commit(); wg_wait<1>();
        mbar_arrive_if(elect && i, bars + 8 * (B_EA + rslot(i - 1)));
        mma_ss64<0, 0, 1>(cX, df + 4, dx + 4);
        mma_ss64<0, 0, 1>(cX, df + 6, dx + 6);
        if (i == 0 && tid == 0) PROF_EV(1);
        mbar_wait(bars + 8 * (B_FX + 2 * i + 1), 0);
        wg_fence();
#pragma unroll
        for (int k = 0; k < 4; k++) mma_ss64<0, 0, 1>(cX, df + (512 + k * 2), dx + (1024 + k * 2));
        wg_commit();
        waitA(i);
        wg_fence();
        const uint64_t da = d128(dX + i * 1024), db = d128(dN + RING + i * 1024);
        mma_ss128<0, 1, 2>(cA, da, db, i);
        wg_commit(); wg_wait<1>();
        mbar_arrive_if(elect, bars + 8 * (B_FE + i));
#pragma unroll
        for (int k = 1; k < 4; k++) mma_ss128<0, 1, 1>(cA, da + k * 2, db + k * 128);
        wg_commit();
      }
      fence_regs<0, 32>(cX);
#pragma unroll
      for (int e = 0; e < 16; e++) yf[e] = pack_pin(cX[2 * e], cX[2 * e + 1]);
      if (tid == 0) { PROF_EV(2); PROF_CK(42); }
      {
        waitA(4); mbar_wait(bars + 8 * B_E0, 0);
        const uint64_t de = d128(dN + (wg ? RING : OFF_XB >> 4));
        wg_fence();
        mma_rs128<0, 1, 0>(cB, yf[0], yf[1], yf[2], yf[3], de);
        wg_commit();
        wg_wait<1>();
        freeA(3);
#pragma unroll
        for (int k = 1; k < 4; k++) mma_rs128<0, 1, 1>(cB, yf[4 * k], yf[4 * k + 1], yf[4 * k + 2], yf[4 * k + 3], de + k * 128);
        wg_commit();
      }
      bool rel = false;
      auto acquire = [&](int n) {
        rel = elect;
        if (!mbar_try(bars + 8 * (B_FA + rslot(n)), rpar(n))) { wg_wait<0>(); freeA(n - 1); rel = false; waitA(n); }
      };
      auto freeP = [&](int n) { mbar_arrive_if(rel, bars + 8 * (B_EA + rslot(n - 1))); };
      auto ffn_step = [&](auto first, auto split, float (&acc)[64], int n, int kb, auto done, auto work) {
        constexpr int SPLIT = decltype(split)::value;
        acquire(n);
        wg_fence();
        const uint64_t dx = d128(dX + kb * 1024), db = d128(dN + RING + rslot(n) * 1024);
        mma_ss128<0, 1, decltype(first)::value>(acc, dx, db, kb);
#pragma unroll
        for (int k = 1; k < SPLIT; k++) mma_ss128<0, 1, 1>(acc, dx + k * 2, db + k * 128);
        wg_commit();
        work();
        wg_wait<1>();
        freeP(n);
        done();
        if (SPLIT < 4) {
          wg_fence();
#pragma unroll
          for (int k = SPLIT; k < 4; k++) mma_ss128<0, 1, 1>(acc, dx + k * 2, db + k * 128);
          wg_commit();
        }
      };
      {
        const int s0 = 2 * rb + wg, kr = 2 * ((s0 & 1) | ((s0 & 4) >> 1));
        const int m = lane >> 3, r = lane & 7;
        const uint32_t a0 = sb + OFF_XB + wg * 8192 + ((2 * (m >> 1) + (r >> 2)) * 2 + (w & 1)) * 256 + (m & 1) * 128 + (((2 * (r & 3) + ((w >> 1) ^ (r >> 2))) ^ (kr + (m & 1))) << 4);
        ffn_step(IC<1>(), IC<4>(), cA, 5, 4, [&] { fence_regs<0, 64>(cB); }, nop);
        asm volatile("bar.sync 5, 256;" ::: "memory");
        auto stage = [&](int i) {
          stsm4t(a0 + i * 2048, pack_bf16(cB[8 * i] - cB[34 + 8 * i], cB[8 * i + 1] - cB[35 + 8 * i]),
                 pack_bf16(cB[32 + 8 * i] + cB[8 * i + 2], cB[33 + 8 * i] + cB[8 * i + 3]),
                 pack_bf16(cB[8 * i + 4] - cB[38 + 8 * i], cB[8 * i + 5] - cB[39 + 8 * i]),
                 pack_bf16(cB[36 + 8 * i] + cB[8 * i + 6], cB[37 + 8 * i] + cB[8 * i + 7]));
          if (j == 0 && w == 0) {
            const uint32_t a1 = r ? sb + OFF_SP + 1024 : sb + OFF_SP + wg * 512 + (m & 1) * 256 + (m >> 1) * 128;
#pragma unroll
            for (int n = 2 * i; n < 2 * i + 2; n++)
              asm volatile("stmatrix.sync.aligned.m8n8.x4.shared.b16 [%0], {%1,%2,%3,%4};" ::"r"(a1 + ((n ^ (kr + (m >> 1)) ^ r) << 4)),
                           "r"(pack_bf16(cB[4 * n], cB[4 * n + 1])), "r"(pack_bf16(cB[4 * n + 2], cB[4 * n + 3])),
                           "r"(pack_bf16(cB[32 + 4 * n], cB[33 + 4 * n])), "r"(pack_bf16(cB[34 + 4 * n], cB[35 + 4 * n])) : "memory");
          }
        };
        auto publish = [&] {
          asm volatile("fence.proxy.async.shared::cta;" ::: "memory");
          __syncwarp();
          mbar_arrive_if(lane == 0, bars + 8 * (B_XS + wg));
          if (tid == 0) PROF_EV(3);
        };
        stage(0);
        ffn_step(IC<1>(), IC<FSPLIT>(), cA, 6, 5, nop, nop);
        stage(1);
        ffn_step(IC<1>(), IC<FSPLIT>(), cA, 7, 6, nop, nop);
        stage(2);
        ffn_step(IC<1>(), IC<2>(), cA, 8, 7, [&] { stage(3); }, nop);
        publish();
      }
      uint32_t gb0 = 0, gb1 = 0;
      uint32_t ob[2] = {0, 0};
      auto glu = [&](auto& acc, int half, int ho, int i0, int i1) {
#pragma unroll
        for (int i = i0; i < i1; i++)
          asm volatile("{\n.reg .b32 a, b;\ncvt.rn.relu.bf16x2.f32 a, %2, %1;\ncvt.rn.bf16x2.f32 b, %4, %3;\nmul.rn.bf16x2 a, a, b;\nmul.rn.bf16x2 %0, a, %5;\n}"
                       : "=r"(h[ho + i]) : "f"(acc[2 * i]), "f"(acc[2 * i + 1]), "f"(acc[half + 2 * i]), "f"(acc[half + 1 + 2 * i]), "r"(ob[i & 1]) : "memory");
      };
      ffn_step(IC<2>(), IC<1>(), cB, 9, zero, nop, nop);
#pragma unroll 1
      for (int kb = 1; kb < 8; kb++)
        ffn_step(IC<1>(), IC<FSPLIT>(), cB, 9 + kb, kb, nop, [&] {
          if (kb == GKB) {
            mbar_wait(bars + 8 * B_G, 0);
            asm volatile("ld.shared.u32 %0, [%2];\nld.shared.u32 %1, [%2+32];" : "=r"(gb0), "=r"(gb1) : "r"(sb + OFF_G + (wg * 64 + w * 16 + g) * 4) : "memory");
          } else if (kb == 5 + 2 * wg) {
            ob[0] = pack_bf16(1.0f - bf_hi(gb0), 1.0f - bf_hi(gb0)); ob[1] = pack_bf16(1.0f - bf_hi(gb1), 1.0f - bf_hi(gb1));
            glu(cA, 32, 0, 0, 16);
          }
        });
      const uint32_t tag = gb0 & 1;
      const float g0 = bf_hi(gb0), g1 = bf_hi(gb1);
      if (tid == 0) { PROF_EV(4); PROF_CK(43); }
      auto m_step = [&](auto first, int i) {
        acquire(17 + i);
        wg_fence();
        const uint64_t dx = d128(dX + i * 2048), dm = d64(dN + RING + rslot(17 + i) * 1024);
        mma_ss64<0, 1, decltype(first)::value>(ct, dx, dm);
#pragma unroll
        for (int k = 1; k < MSPLIT; k++) mma_ss64<0, 1, 1>(ct, dx + ((k >> 2) * 1024 + (k & 3) * 2), dm + k * 64);
        wg_commit();
        wg_wait<1>();
        freeP(17 + i);
        wg_fence();
#pragma unroll
        for (int k = MSPLIT; k < 8; k++) mma_ss64<0, 1, 1>(ct, dx + ((k >> 2) * 1024 + (k & 3) * 2), dm + k * 64);
        wg_commit();
      };
      m_step(IC<0>(), 0);
#pragma unroll 1
      for (int i = 1; i < 5; i++) {
        if (i == 1 + 2 * wg) glu(cB, 32, 16, 0, 16);
        if (i < 4) m_step(IC<1>(), i);
      }
      if (tid == 0) { PROF_EV(5); PROF_CK(44); }
      ffn_step(IC<0>(), IC<1>(), cC, 21, 0, nop, nop);
#pragma unroll 1
      for (int kb = 1; kb < 8; kb++)
        ffn_step(IC<1>(), IC<FSPLIT>(), cC, 21 + kb, kb, [&] { mbar_arrive_if(elect && !(kb & 1), bars + 8 * (B_ET + (kb >> 1) - 1)); }, [&] {
          if (kb == 1 + wg) glu(ct, 16, 48, 0, 8);
        });

      auto twait = [&](uint32_t bar, uint32_t par, int) { mbar_wait(bar, par); };
      const int fo = warp * 128 + lane;
      auto fetch = [&](uint4 (&pv)[4], int z) {
        twait(bars + 8 * (z < 4 ? B_Z + 2 * z + wg : z < 6 ? B_HP + z - 4 : B_HP + 2 + wg), 0, 8 + z);
        const uint8_t* src = smem + (z < 4 ? OFF_Z - z * U : z == 4 ? OFF_T : (z - 5) * U) + fo * 16;
#pragma unroll
        for (int i = 0; i < 4; i++) pv[i] = *(const uint4*)(src + i * 512);
      };
      const uint32_t peerZ = mapa(sb + OFF_Z + fo * 16, rank ^ 1), peerB = mapa(bars + 8 * (B_Z + wg), rank ^ 1);
      auto tile_mma = [&](auto off, int t, int k0, int k1, bool fresh = false) {
        constexpr int O = decltype(off)::value;
        const uint64_t db = d128(dN + (t & 3) * (TB >> 4)), dw = db + rank * 256, dm = db + (rank ? 0 : 1536);
#pragma unroll
        for (int k = k0; k < k1; k++) {
          if (k == 0 && O == 0) mma_rs64<O, 1, 2>(ct, h[0], h[1], h[2], h[3], dw, zero);
          else if (k < 14) mma_rs64<O, 1, 1>(ct, h[4 * k], h[4 * k + 1], h[4 * k + 2], h[4 * k + 3], k < 12 ? dw + k * 128 : dm + (k - 12) * 128);
          else if (k == 14 && fresh) mma_rs64<O, 1, 0>(ct, yf[0], yf[1], yf[2], yf[3], db + k * 128);
          else if (k == 14) mma_rs64<O, 1, 2>(ct, yf[0], yf[1], yf[2], yf[3], db + k * 128, zero);
          else mma_rs64<O, 1, 1>(ct, yf[4 * k - 56], yf[4 * k - 55], yf[4 * k - 54], yf[4 * k - 53], db + k * 128);
        }
      };
      uint4 pv[4];
      const uint32_t sgn = rank ? 0x80008000u : 0u;
      auto even_end = [&](int t, int k0, bool fresh) {
        wg_fence();
        tile_mma(IC<32>(), t, 14, 18, fresh);
        wg_commit();
        tile_mma(IC<0>(), t, k0, 14);
        wg_commit();
        wg_wait<1>();
        fence_regs<32, 32>(ct);
#pragma unroll
        for (int i = 0; i < 4; i++)
          pv[i] = make_uint4(pack_pin(ct[32 + 8 * i], ct[33 + 8 * i]) ^ sgn, pack_pin(ct[34 + 8 * i], ct[35 + 8 * i]) ^ sgn,
                             pack_pin(ct[36 + 8 * i], ct[37 + 8 * i]) ^ sgn, pack_pin(ct[38 + 8 * i], ct[39 + 8 * i]) ^ sgn);
      };
      auto odd_head = [&](int t) {
        twait(bars + 8 * (B_FT + (t & 3)), t >> 2, t);
        wg_fence();
        tile_mma(IC<32>(), t, 0, OA);
        wg_commit();
        if (t < 4) twait(bars + 8 * (t == 1 ? B_RD0 : B_RDY), 0, 14 + t);
        wg_wait<1>();
        mbar_arrive_if(elect && t < 6, bars + 8 * (B_ET + t - 1));
        fence_regs<0, 32>(ct);
        wg_fence();
#pragma unroll
        for (int i = 0; i < 4; i++) {
          asm volatile("st.async.weak.shared::cluster.mbarrier::complete_tx::bytes.v4.b32 [%0], {%2,%3,%4,%5}, [%1];" ::"r"(peerZ - (t >> 1) * U + i * 512),
                       "r"(peerB + 16 * (t >> 1)), "r"(add_bf2(pv[i].x, pack_bf16(ct[8 * i], ct[8 * i + 1]))), "r"(add_bf2(pv[i].y, pack_bf16(ct[8 * i + 2], ct[8 * i + 3]))),
                       "r"(add_bf2(pv[i].z, pack_bf16(ct[8 * i + 4], ct[8 * i + 5]))), "r"(add_bf2(pv[i].w, pack_bf16(ct[8 * i + 6], ct[8 * i + 7]))) : "memory");
          tile_mma(IC<32>(), t, OA + i, OA + i + 1);
        }
        wg_commit();
      };
      asm volatile("barrier.cluster.wait.aligned;" ::: "memory");
      twait(bars + 8 * B_FT, 0, 0);
      if (wg) asm volatile("bar.sync 6, 256;" ::: "memory");
      wg_fence();
      tile_mma(IC<0>(), 0, 0, T0A);
      wg_commit();
      if (!wg) asm volatile("bar.arrive 6, 256;" ::: "memory");
      waitA(29 + wg);
      wg_wait<1>();
      mbar_arrive_if(elect, bars + 8 * (B_ET + 3));
      glu(cC, 32, 32, 0, 16);
      if (tid == 0) PROF_EV(6);
      if (tid == 128) PROF_EV(27);
      mbar_wait(bars + 8 * (j == 0 ? B_T : B_TL), 0);
      if (tid == 0) { PROF_EV(7); PROF_CK(45); }
      wg_fence();
      {
        const uint64_t dt = d128(dN + (OFF_T >> 4) + wg * 512), de = d128(dK + RING + (1 + wg) * 1024);
        mma_ss64<0, 1, 0>(ci, de, dt);
        mma_ss64<32, 1, 0>(ci, de + 512, dt);
#pragma unroll
        for (int k = 1; k < 4; k++) {
          mma_ss64<0, 1, 1>(ci, de + k * 2, dt + k * 128);
          mma_ss64<32, 1, 1>(ci, de + (512 + k * 2), dt + k * 128);
        }
        wg_commit();
      }
      tile_mma(IC<0>(), 0, T0A, T0B);
      wg_commit();
      wg_wait<1>();
      if (elect) asm volatile("mbarrier.arrive.shared::cluster.b64 _, [%0];" ::"r"(mapa(bars + 8 * B_RDY, rank ^ 1)) : "memory");
      mbar_arrive_if(elect, bars + 8 * (B_PZ + 1));
      fence_regs<0, 64>(ci);
#pragma unroll
      for (int i = 0; i < 16; i++) {
        const float gg = ((i & 1) ? g1 : g0) * (2.0f / (2048.0f * 512.0f));
        if (i & 2) yf[i] = pack_pin((ci[2 * i] - ci[28 + 2 * i]) * gg, (ci[2 * i + 1] - ci[29 + 2 * i]) * gg);
        else yf[i] = pack_pin((ci[2 * i] + ci[36 + 2 * i]) * gg, (ci[2 * i + 1] + ci[37 + 2 * i]) * gg);
      }
      even_end(0, T0B, true);
      if (tid == 0) PROF_EV(8);
      if (tid == 128) PROF_EV(28);
#pragma unroll 1
      for (int t = 1; t < 7; t += 2) {
        odd_head(t);
        wg_fence();
        tile_mma(IC<32>(), t, OA + 4, 14);
        wg_commit();
        const int zo = t >> 1, owner = rb * 8 + 2 * ((q4 + zo + 1) & 3) + rank;
        uint4* dst = ws->part + (size_t)(owner * 3 + zo) * 1024 + fo;
        auto send = [&] {
          fence_regs<32, 32>(ct);
#pragma unroll
          for (int i = 0; i < 4; i++)
            asm volatile("st.relaxed.gpu.global.v4.u32 [%0], {%1,%2,%3,%4};" ::"l"(dst + i * 32),
                         "r"((add_bf2(pv[i].x, pack_bf16(ct[32 + 8 * i], ct[33 + 8 * i])) & ~1u) | tag), "r"(add_bf2(pv[i].y, pack_bf16(ct[34 + 8 * i], ct[35 + 8 * i]))),
                         "r"(add_bf2(pv[i].z, pack_bf16(ct[36 + 8 * i], ct[37 + 8 * i]))), "r"(add_bf2(pv[i].w, pack_bf16(ct[38 + 8 * i], ct[39 + 8 * i]))) : "memory");
          hint_add_if(lane == 0, &ws->cntP[32 * owner + 8 * (zo + (zo == 2 ? wg : 0))]);
        };
        if (t == 5) fetch(pv, 2);
        twait(bars + 8 * (B_FT + ((t + 1) & 3)), (t + 1) >> 2, t + 1);
        wg_fence();
        tile_mma(IC<0>(), t + 1, 0, TH);
        wg_commit();
        wg_wait<1>();
        mbar_arrive_if(elect && t < 5, bars + 8 * (B_ET + t));
        if (t == 5) send(); else fetch(pv, zo);
        wg_fence();
        tile_mma(IC<0>(), t + 1, TH, EB);
        wg_commit();
        if (t != 5) send();
        even_end(t + 1, EB, false);
      }
      {
        uint4 p1[4], p2[4];
        auto acc4 = [&](uint4 (&d)[4], const uint4 (&a)[4]) {
#pragma unroll
          for (int i = 0; i < 4; i++) { d[i].x = add_bf2(d[i].x, a[i].x); d[i].y = add_bf2(d[i].y, a[i].y); d[i].z = add_bf2(d[i].z, a[i].z); d[i].w = add_bf2(d[i].w, a[i].w); }
        };
        auto add32 = [&](const uint4 (&a)[4]) {
#pragma unroll
          for (int i = 0; i < 4; i++) {
            const uint32_t u[4] = {a[i].x, a[i].y, a[i].z, a[i].w};
#pragma unroll
            for (int e = 0; e < 4; e++) { ct[32 + 8 * i + 2 * e] += bf_lo(u[e]); ct[33 + 8 * i + 2 * e] += bf_hi(u[e]); }
          }
        };
        odd_head(7);
        fetch(pv, 4);
        fetch(p1, 5);
        wg_fence();
        tile_mma(IC<32>(), 7, OA + 4, OB);
        wg_commit();
        uint32_t bad = 0;
#pragma unroll
        for (int i = 0; i < 4; i++) { bad |= (pv[i].x ^ tag) | (p1[i].x ^ tag); pv[i].x &= ~1u; p1[i].x &= ~1u; }
        acc4(pv, p1);
        fetch(p1, 3);
        wg_fence();
        tile_mma(IC<32>(), 7, OB, 14);
        wg_commit();
        if (tid == 0) { PROF_EV(9); PROF_CK(46); }
        if (tid == 128) PROF_EV(29);
        fetch(p2, 6);
        if (tid == 0) PROF_EV(24);
        wg_wait<0>();
        fence_regs<32, 32>(ct);
#pragma unroll
        for (int i = 0; i < 4; i++) bad |= p2[i].x ^ tag;
        if (__any_sync(0xffffffffu, bad & 1)) {
          const uint4* src = ws->part + (size_t)(rb * 8 + j) * 3 * 1024 + fo;
          uint4 p0[4];
          int n = 0;
          do {
            bad = 0;
#pragma unroll
            for (int i = 0; i < 4; i++) {
              pv[i] = ld_x4(src + i * 32); p0[i] = ld_x4(src + 1024 + i * 32); p2[i] = ld_x4(src + 2048 + i * 32);
              bad |= (pv[i].x ^ tag) | (p0[i].x ^ tag) | (p2[i].x ^ tag);
            }
            if (++n > (1 << 21)) __trap();
          } while (__any_sync(0xffffffffu, bad & 1));
#pragma unroll
          for (int i = 0; i < 4; i++) { pv[i].x &= ~1u; p0[i].x &= ~1u; }
          acc4(pv, p0);
        }
#pragma unroll
        for (int i = 0; i < 4; i++) p2[i].x &= ~1u;
        acc4(p1, p2);
        add32(pv); add32(p1);
#pragma unroll
        for (int i = 0; i < 4; i++)
          pv[i] = make_uint4(pack_bf16(ct[32 + 8 * i], ct[33 + 8 * i]), pack_bf16(ct[34 + 8 * i], ct[35 + 8 * i]), pack_bf16(ct[36 + 8 * i], ct[37 + 8 * i]), pack_bf16(ct[38 + 8 * i], ct[39 + 8 * i]));
        if (tid == 0) PROF_EV(14);
        const uint32_t stg = sb + OFF_T + warp * 2048;
        const int mr = (lane & 7) + ((lane >> 3) & 1) * 8, mc = lane >> 4;
#pragma unroll
        for (int i = 0; i < 4; i++)
          asm volatile("stmatrix.sync.aligned.m8n8.x4.shared.b16 [%0], {%1,%2,%3,%4};" ::"r"(stg + mr * 128 + (((2 * i + mc) ^ (mr & 7)) << 4)), "r"(pv[i].x),
                       "r"(pv[i].y), "r"(pv[i].z), "r"(pv[i].w) : "memory");
        __syncwarp();
#pragma unroll
        for (int i = 0; i < 4; i++) {
          const int r = 4 * i + (lane >> 3), c = lane & 7;
          const uint4 v = *(const uint4*)(smem + OFF_T + warp * 2048 + r * 128 + ((c ^ (r & 7)) << 4));
          *(uint4*)(out + (size_t)(2 * rb + wg + 32 * (16 * w + r)) * 512 + 64 * (q4 + 4 * rank) + 8 * c) = v;
        }
      }
      if (tid == 0) { PROF_EV(15); PROF_CK(41); }
      if (tid == 128) PROF_EV(30);
    }
  } else if (warp < 12) {
    asm volatile("setmaxnreg.dec.sync.aligned.u32 104;");
    asm volatile("barrier.cluster.arrive.relaxed.aligned;" ::: "memory");
    const int t = tid - 256, w = warp - 8;
    const uint32_t ep = ld_x1(&ws->epoch[blockIdx.x * 8]);
    const uint32_t tag = (ep + 1) & 1;
    auto w_issue = [&](const CUtensorMap* m) {

      if (elect_one()) { mbar_expect_tx(bars + 8 * (B_WR + w), 3072); tma4d(sb + OFF_T + w * 3072, m, bars + 8 * (B_WR + w), 32 * j, 0, 4 * (rb & 1) + w, rb >> 1); }

          __syncwarp();
    };
    auto gate_rows = [&] {
      const int r = 16 * j + 4 * w + (lane >> 3);
      const uint4* pg = (const uint4*)gate_w + (lane & 7);
      {
        float a = 0.f;
        asm volatile("bar.sync 4, 256;" ::: "memory");
#pragma unroll 1
        for (int hf = 0; hf < 2; hf++) {
          uint4 v[4], u[4];
#pragma unroll
          for (int kb = 0; kb < 4; kb++) v[kb] = __ldg(pg + (4 * hf + kb) * 8);
          mbar_wait(bars + 8 * (B_FE + 1 + 2 * hf), 0);
          if (hf) w_issue(&maps.wr);
#pragma unroll
          for (int kb = 0; kb < 4; kb++) u[kb] = *(const uint4*)(smem + (4 * hf + kb) * U + r * 128 + (((lane ^ r) & 7) << 4));
#pragma unroll
          for (int kb = 0; kb < 4; kb++) {
            const uint32_t uu[4] = {u[kb].x, u[kb].y, u[kb].z, u[kb].w}, vv[4] = {v[kb].x, v[kb].y, v[kb].z, v[kb].w};
#pragma unroll
            for (int e = 0; e < 4; e++) {
              uint32_t pr;
              asm("mul.rn.bf16x2 %0, %1, %2;" : "=r"(pr) : "r"(uu[e]), "r"(vv[e]));
              a += bf_lo(pr) + bf_hi(pr);
            }
          }
        }
#pragma unroll
        for (int o = 4; o; o >>= 1) a += __shfl_xor_sync(0xffffffffu, a, o);
        if ((lane & 7) == 0)
          asm volatile("st.relaxed.gpu.global.u32 [%0], %1;" ::"l"(ws->gate + rb * 128 + r),
                       "r"(pack_bf16(0.f, __fdividef(1.0f, 1.0f + __expf(-bf_lo(pack_bf16(a, 0.f))))) | tag) : "memory");
        if (t == 0) PROF_EV(18);
      }
    };
    {
      const int g = lane >> 2, q = lane & 3;
      uint32_t wf[32];
      if (!helper) {
        gate_rows();
        const uint32_t wa = sb + OFF_T + w * (3072 + 2) + (rb & 1) * 8 + q * 96 + g * 4, wb[2] = {wa + (rb & 1) * 32, wa + 32 - (rb & 1) * 32};
#pragma unroll 1
        for (int ri = 0; ri < 2; ri++) {
          mbar_wait(bars + 8 * (B_WR + w), ri);
#pragma unroll
          for (int n2 = 0; n2 < 32 / WB; n2++) {
            uint32_t v[WB];
#pragma unroll
            for (int i = 0; i < WB; i++) {
              const int e = n2 * WB + i;
              asm volatile("ld.shared.u16 %0, [%1];" : "=r"(v[i]) : "r"(wb[e & 1] + ((e >> 1) & 7) * 384 + (e >> 4) * 2) : "memory");
            }
#pragma unroll
            for (int i = 0; i < WB; i++) wf[n2 * WB + i] = __byte_perm(wf[n2 * WB + i], v[i], 0x5432);
            if (WSLEEP) { asm volatile("nanosleep.u32 %0;" ::"r"(WSLEEP + (v[WB - 1] >> 16)) : "memory"); }
          }
          __syncwarp();
          if (ri == 0) w_issue(&maps.wi);
        }
        asm volatile("bar.sync 1, 128;" ::: "memory");
        if (t == 0) PROF_EV(11);
      } else {
        asm volatile("bar.sync 4, 256;" ::: "memory");
        hint_wait(&ws->cntW[0], (ep + 1) * 128u);
        const uint32_t t0 = (uint32_t)clock();
#pragma unroll 1
        for (;;) {
          uint32_t bad = 0;
#pragma unroll
          for (int i = 0; i < 32; i++) {
            const float2 v = ld_x2((const float2*)ws->Wh + (i >> 4) * 2048 + 16 * w + g + 8 * (i & 1) + 64 * q + ((i >> 1) & 7) * 256);
            wf[i] = __float_as_uint(v.x); bad |= __float_as_uint(v.y) ^ tag;
          }
          if (!__any_sync(0xffffffffu, bad & 1)) break;
          spin_guard(t0);
        }
        if (t == 0) PROF_EV(11);
      }
      if (w == 0 && elect_one()) { mbar_expect_tx(bars + 8 * B_W, 8192); bulk_load(sb + OFF_D, dtab, 8192, bars + 8 * B_W); }
      asm volatile("barrier.cluster.wait.aligned;" ::: "memory");
      mbar_wait(bars + 8 * B_W, 0);
      mbar_wait(bars + 8 * B_HX, 0);
      if (t == 0) PROF_EV(12);
      const uint32_t dd = (sb & 0x3FFFF) >> 4;
      const uint64_t dF = d128((dd + (OFF_D >> 4)) | (512u << 16)), dI = d128((dd + (OFF_D >> 4)) | (1u << 16)), dA = d128((dd + (OFF_XB >> 4)) | (512u << 16));
      float az[32];
      const int zero = blockIdx.x >> 16;
      uint32_t pf[32];
#pragma unroll
      for (int mt = 0; mt < 2; mt++) {
        wg_fence();
        if (mt == 0) mma_ss64<0, 3, 0>(az, dA, dF);
        else mma_ss64<0, 3, 2>(az, dA + 512, dF, zero);
#pragma unroll
        for (int k = 1; k < 4; k++) mma_ss64<0, 3, 1>(az, dA + (mt * 512 + k * 128), dF + k * 128);
        wg_commit();
        wg_wait<0>();
        fence_regs<0, 32>(az);
#pragma unroll
        for (int i = 0; i < 16; i++) {
          const float wr = bf_lo(wf[16 * mt + i]), wi = bf_hi(wf[16 * mt + i]);
          pf[16 * mt + i] = pack_pin(fmaf(az[2 * i], wr, -az[2 * i + 1] * wi), fmaf(az[2 * i], wi, az[2 * i + 1] * wr));
        }
      }
      if (t == 0) PROF_EV(16);
      {
        const int m = lane >> 3, r = lane & 7;
        const int sl = 2 * (m >> 1) + ((r >> 1) & 1) + 4 * (r >> 2);
        const uint32_t a0 = sb + OFF_XB + w * 4096 + sl * 64 + (((((m ^ rb) & 1) * 2 + (r & 1)) ^ (sl >> 1)) << 4);
        uint32_t pk[16];
#pragma unroll
        for (int mt = 0; mt < 3; mt++) {
          if (mt < 2) {
            wg_fence();
            mma_rs64<0, 0, 2>(az, pf[16 * mt], pf[16 * mt + 1], pf[16 * mt + 2], pf[16 * mt + 3], dI, mt ? (int)helper : zero);
#pragma unroll
            for (int k = 1; k < 4; k++) mma_rs64<0, 0, 1>(az, pf[16 * mt + 4 * k], pf[16 * mt + 4 * k + 1], pf[16 * mt + 4 * k + 2], pf[16 * mt + 4 * k + 3], dI + k * 2);
            wg_commit();
          }
          if (mt > 0 && !helper) {
#pragma unroll
            for (int i = 0; i < 4; i++) stsm4t(a0 + (mt - 1) * 2048 + i * 512, pk[4 * i], pk[4 * i + 1], pk[4 * i + 2], pk[4 * i + 3]);
          }
          if (mt < 2) {
            wg_wait<0>();
            fence_regs<0, 32>(az);
#pragma unroll
            for (int i = 0; i < 16; i++) pk[i] = pack_pin(az[2 * i], az[2 * i + 1]);
          }
        }
      }
      if (helper) {
#pragma unroll
        for (int i = 0; i < 16; i++) {
          const int n = i >> 1, s0 = 8 * (n >> 1) + 2 * (n & 1) + (q & 1) + 4 * (q >> 1);
          if ((n & 1) == (int)(blockIdx.x & 1)) st_u2(ws->Ts + s0 * 64 + 16 * w + g + 8 * (i & 1), pack_bf16(az[2 * i], az[2 * i + 1]), tag);
        }
        __syncwarp();
        hint_add_if(lane == 0, &ws->cntH[0]);
        if (t == 0) { ws->epoch[blockIdx.x * 8] = ep + 1; PROF_EV(13); }
      } else {
        asm volatile("fence.proxy.async.shared::cta;" ::: "memory");
        __syncwarp();
        if (elect_one()) {
          if (t == 0) PROF_EV(17);
          if (SPACE) __nanosleep(SPACE * w);
          asm volatile("cp.async.bulk.tensor.4d.global.shared::cta.bulk_group [%0, {%2, %3, %4, %5}], [%1];" ::"l"(&maps.ts), "r"(sb + OFF_XB + w * 4096),
                       "r"(32 * rank), "r"(0), "r"(2 * q4), "r"(4 * rb + w) : "memory");
          bulk_done_signal(&ws->cntT[32 * q4]);
          asm volatile("mbarrier.arrive.shared::cluster.b64 _, [%0];" ::"r"(mapa(bars + 8 * B_RD0, rank ^ 1)) : "memory");
          if (t == 96) PROF_EV(13);
        }
        __syncwarp();
        if (j == 0) {
          hint_wait(&ws->cntH[0], (ep + 1) * 8u);
          const uint32_t t0 = (uint32_t)clock();
          float2 v;
          do { v = ld_x2((const float2*)ws->Ts + 2 * rb * 64 + t); spin_guard(t0); } while (__any_sync(0xffffffffu, (__float_as_uint(v.y) ^ tag) & 1));
          mbar_wait(bars + 8 * B_TL, 0);
          const uint32_t u = __float_as_uint(v.x);
          *(uint16_t*)(smem + OFF_T + t * 128 + ((t & 7) << 4)) = (uint16_t)u;
          *(uint16_t*)(smem + OFF_T + t * 128 + (((t & 7) ^ 1) << 4)) = (uint16_t)(u >> 16);
          asm volatile("fence.proxy.async.shared::cta;" ::: "memory");
          __syncwarp();
          mbar_arrive_if(lane == 0, bars + 8 * B_T);
        }
      }
    }
  } else {
    asm volatile("setmaxnreg.dec.sync.aligned.u32 24;");
    auto xf_load = [&](int q) {
      const uint32_t fb = bars + 8 * (B_FX + q);
      mbar_expect_tx(fb, U + 8192);
      tma3d(sb + q * U, &maps.x, fb, 64 * q, 0, 2 * rb);
      if (q >= 4) mbar_wait(bars + 8 * (B_FE + ((q - 4) >> 1)), 0);
      tma2d(sb + OFF_XB + (q & 3) * 8192, &maps.ft, fb, 64 * q, 64 * j);
    };
    if (elect_one()) {
      if (warp == 14) {
#pragma unroll
        for (int i = 0; i < B_FT; i++) mbar_init(bars + 8 * i, 1);
        asm volatile("fence.mbarrier_init.release.cluster;" ::: "memory");
        if (!helper) {
#pragma unroll 1
          for (int n = 0; n < 2; n++) {
            const uint32_t fb = bars + 8 * (B_FA + n);
            xf_load(2 * n); xf_load(2 * n + 1);
            mbar_expect_tx(fb, U);
            tma2d(sb + OFF_RING + n * U, &maps.g64, fb, f_full, 64 * n);
            tma2d(sb + OFF_RING + n * U + 8192, &maps.u64, fb, f_full, 64 * n);
          }
        }
      } else if (warp == 15) {
#pragma unroll
        for (int i = B_FT; i < NBAR; i++) mbar_init(bars + 8 * i, i < B_EA ? 1 : i < B_T ? 2 : 4);
#pragma unroll
        for (int i = 0; i < 8; i++) mbar_expect_tx(bars + 8 * (B_Z + i), U / 2);
        asm volatile("fence.mbarrier_init.release.cluster;" ::: "memory");
        asm volatile("fence.proxy.async.shared::cta;" ::: "memory");
      }
    }
    __syncwarp();
    asm volatile("bar.arrive 0, 384;" ::: "memory");
    asm volatile("bar.arrive 4, 256;" ::: "memory");
    __syncwarp();
    asm volatile("barrier.cluster.arrive.relaxed.aligned;" ::: "memory");
    asm volatile("bar.sync 3, 128;" ::: "memory");
    if (warp == 15 && !helper) {
        mbar_wait(bars + 8 * B_FE, 0);
        const uint32_t tag = (ld_x1(&ws->epoch[blockIdx.x * 8]) + 1) & 1;
        const int c = lane >> 4, jj = 16 * blockIdx.x + (lane & 15), jm = (2048 - jj) & 2047;
        const unsigned short* pr = (const unsigned short*)w_r + 256 * c;
        const unsigned short* pi = (const unsigned short*)w_i + 256 * c;
        const float wr = 0.25f * (bf_lo(__ldg(pr + jj * 257)) + bf_lo(__ldg(pr + jm * 257)));
        const float wi = 0.25f * (bf_lo(__ldg(pi + jj * 257)) - bf_lo(__ldg(pi + jm * 257)));
        st_u2(ws->Wh + c * 2048 + jj, c ? pack_bf16(-wi, wr) : pack_bf16(wr, wi), tag);
        __syncwarp();
        hint_add_if(lane == 0, &ws->cntW[0]);
        mbar_wait(bars + 8 * B_XS, 0);
        const uint32_t t0 = (uint32_t)clock();
        uint4 v;
        do { v = ld_x4(ws->gate + rb * 128 + 4 * lane); spin_guard(t0); } while (__any_sync(0xffffffffu, ((v.x ^ tag) | (v.y ^ tag) | (v.z ^ tag) | (v.w ^ tag)) & 1));
        *(uint4*)(smem + OFF_G + lane * 16) = v;
        __syncwarp();
        mbar_arrive_if(lane < 4, bars + 8 * B_G);
      }
    auto part_load = [&](int i, unsigned ep1) {
      const uint32_t bytes = i < 2 ? U : U / 2;
      mbar_wait(bars + 8 * (B_PZ + (i == 0)), 0);
      mbar_expect_tx(bars + 8 * (B_HP + i), bytes);
      flag_wait(&ws->cntP[32 * (rb * 8 + j) + 8 * i], ep1 * (i < 2 ? 8u : 4u));
      bulk_load(sb + (i == 0 ? OFF_T : i == 1 ? 0 : i * (U / 2)), ws->part + (size_t)(rb * 8 + j) * 3072 + (i < 2 ? i * 1024 : 1024 + i * 512), bytes, bars + 8 * (B_HP + i));
      if (i == 2) PROF_EV(26);
    };
    if ((!helper || warp == 15) && elect_one()) {
      if (warp < 14) {
        const int p = warp - 12;
#pragma unroll 1
        for (int i = 4 + p; i < 14; i += 2) asm volatile("prefetch.tensormap [%0];" ::"l"((const char*)&maps + i * 128) : "memory");
#pragma unroll 1
        for (int n = 2; n < 31; n++) {
          const bool table = n == 4 || n >= 29;
          const bool half = n >= 17 && n < 21;
          const int q = n < 4 ? n : n < 17 ? n - 1 : n - 5;
          const CUtensorMap* m = table ? &maps.e : half ? &maps.g32 + p : &maps.g64 + p;
          const int c0 = table ? 0 : half ? f_half : f_full + 64 * (q >> 3);
          const int c1 = table ? (2 * rb + ((n & 1) ^ 1)) * 128 + 64 * p : half ? 128 * (n - 17) : 64 * (q & 7);
          const uint32_t fb = bars + 8 * (B_FA + (n & 3)), dst = sb + OFF_RING + (n & 3) * U + p * 8192;
          if (n < 4) mbar_wait(bars + 8 * (B_FE + n - 2), 0);
          else mbar_wait(bars + 8 * (B_EA + (n & 3)), ((n >> 2) & 1) ^ 1);
          tma2d(dst, m, fb, c0, c1);
          if (p == 0) mbar_expect_tx(fb, U);
        }
        part_load(2 + p, ld_x1(&ws->epoch[blockIdx.x * 8]) + 1);
      } else if (warp == 15) {
        const unsigned ep1 = ld_x1(&ws->epoch[blockIdx.x * 8]) + 1;
        flag_wait(&ws->cntX[helper ? 0 : 32 * j], ep1 * 16u);
        PROF_EV(22);
        mbar_expect_tx(bars + 8 * B_HX, U);
        bulk_load(sb + OFF_XB, ws->X + (size_t)(helper ? 128 : 16 * j + rb) * 8192, U, bars + 8 * B_HX);
        if (!helper) {
          flag_wait(&ws->cntT[32 * q4], ep1 * 128u);
          PROF_EV(23);
          mbar_expect_tx(bars + 8 * B_TL, U);
          tma3d(sb + OFF_T, &maps.t, bars + 8 * B_TL, 64 * j, 0, 2 * rb);
          part_load(0, ep1); part_load(1, ep1);
          mbar_wait(bars + 8 * (B_HP + 2), 0); mbar_wait(bars + 8 * (B_HP + 3), 0);
          ws->epoch[blockIdx.x * 8] = ep1;
        }
      } else {
#pragma unroll 1
        for (int q = 4; q < 8; q++) xf_load(q);
        mbar_wait(bars + 8 * (B_FE + 2), 0);
        mbar_expect_tx(bars + 8 * B_E0, U);
        tma2d(sb + OFF_XB, &maps.e, bars + 8 * B_E0, 0, 2 * rb * 128);
        tma2d(sb + OFF_XB + 8192, &maps.e, bars + 8 * B_E0, 0, 2 * rb * 128 + 64);
#pragma unroll 1
        for (int h2 = 0; h2 < 2; h2++) {
          const int s0 = 2 * rb + h2, sg = (s0 & ~6) | ((s0 & 2) << 1) | ((s0 & 4) >> 1);
          mbar_wait(bars + 8 * (B_XS + h2), 0);
#pragma unroll 1
          for (int c = 0; c < 2; c++) {
            asm volatile("cp.async.bulk.tensor.4d.global.shared::cta.bulk_group [%0, {%2, %3, %4, %5}], [%1];" ::"l"(&maps.xs),
                         "r"(sb + OFF_XB + h2 * 8192 + c * 4096), "r"(0), "r"(sg), "r"(0), "r"(16 * j + 8 * c) : "memory");
            if (j == 0)
              asm volatile("cp.async.bulk.global.shared::cta.bulk_group [%0], [%1], 256;" ::"l"(ws->X + 128 * 8192 + c * 4096 + sg * 128),
                           "r"(sb + OFF_SP + h2 * 512 + c * 256) : "memory");
            if (SPACE && h2 + c < 2) __nanosleep(SPACE);
          }
        }
        bulk_done_signal(&ws->cntX[32 * j]);
        PROF_EV(20);
#pragma unroll 1
        for (int t = 0; t < 8; t++) {
          const int col = 64 * (((q4 + 1 + (t >> 1)) & 3) + 4 * ((t & 1) ? rank : 1 - rank));
          const uint32_t fb = bars + 8 * (B_FT + (t & 3)), dst = sb + (t & 3) * TB;
          mbar_wait(bars + 8 * (B_ET + (t < 3 ? t + 1 : t & 3)), t >> 2);
          mbar_expect_tx(fb, (t & 1) ? 28672 : TB);
          tma2d(dst, &maps.d224, fb, col, 224 * j);
          if (!(t & 1)) tma3d(dst + 28672, &maps.fg, fb, col ^ 256, 16 * rank, 4 * q4);
        }
      }
    }
  }
}

typedef CUresult (*EncodeFn)(CUtensorMap*, CUtensorMapDataType, cuuint32_t, void*, const cuuint64_t*, const cuuint64_t*, const cuuint32_t*,
                             const cuuint32_t*, CUtensorMapInterleave, CUtensorMapSwizzle, CUtensorMapL2promotion, CUtensorMapFloatOOBfill);

static void encode(EncodeFn f, CUtensorMap* m, const void* base, int rank, const cuuint64_t* dims, const cuuint64_t* strides, const cuuint32_t* box,
                   CUtensorMapSwizzle sw) {
  cuuint32_t es[5] = {1, 1, 1, 1, 1};
  f(m, CU_TENSOR_MAP_DATA_TYPE_BFLOAT16, rank, (void*)base, dims, strides, box, es, CU_TENSOR_MAP_INTERLEAVE_NONE, sw,
    CU_TENSOR_MAP_L2_PROMOTION_L2_128B, CU_TENSOR_MAP_FLOAT_OOB_FILL_NONE);
}

extern "C" void kernel_launch(void* const* d_in, const int* in_sizes, int n_in, void* d_out, int out_size) {
  (void)in_sizes; (void)n_in; (void)out_size;
  const __nv_bfloat16* x = (const __nv_bfloat16*)d_in[0];
  const __nv_bfloat16* w_r = (const __nv_bfloat16*)d_in[1];
  const __nv_bfloat16* w_i = (const __nv_bfloat16*)d_in[2];
  const __nv_bfloat16* Wg = (const __nv_bfloat16*)d_in[4];
  const __nv_bfloat16* Wu = (const __nv_bfloat16*)d_in[5];
  const __nv_bfloat16* Wd = (const __nv_bfloat16*)d_in[6];
  const __nv_bfloat16* gw = (const __nv_bfloat16*)d_in[7];

  void* fp = nullptr; cudaDriverEntryPointQueryResult qr;
  cudaGetDriverEntryPoint("cuTensorMapEncodeTiled", &fp, cudaEnableDefault, &qr);
  EncodeFn enc = (EncodeFn)fp;
  void *pFT, *pET, *pDT, *pW;
  cudaGetSymbolAddress(&pDT, g_DT); cudaGetSymbolAddress(&pW, g_work);
  void *pX = ((Work*)pW)->X, *pT = ((Work*)pW)->T;
  cudaGetSymbolAddress(&pFT, g_FT); cudaGetSymbolAddress(&pET, g_ET);

  Maps mp;
  const CUtensorMapSwizzle S128 = CU_TENSOR_MAP_SWIZZLE_128B, S64 = CU_TENSOR_MAP_SWIZZLE_64B;
  { cuuint64_t d[3] = {512, 64, 32}, s[2] = {32768, 1024}; cuuint32_t b[3] = {64, 64, 2}; encode(enc, &mp.x, x, 3, d, s, b, S128); }
  { cuuint64_t d[2] = {512, 512}, s[1] = {1024}; cuuint32_t b[2] = {64, 64}; encode(enc, &mp.ft, pFT, 2, d, s, b, S128); }
  { cuuint64_t d[4] = {128, 32, 2, 129}, s[3] = {256, 8192, 16384}; cuuint32_t b[4] = {128, 1, 2, 8}; encode(enc, &mp.xs, pX, 4, d, s, b, CU_TENSOR_MAP_SWIZZLE_NONE); }
  { cuuint64_t d[4] = {64, 32, 8, 64}, s[3] = {65536, 128, 1024}; cuuint32_t b[4] = {32, 32, 2, 1}; encode(enc, &mp.ts, pT, 4, d, s, b, S64); }
  { cuuint64_t d[3] = {512, 32, 16}, s[2] = {1024, 32768}; cuuint32_t b[3] = {64, 16, 4}; encode(enc, &mp.fg, pFT, 3, d, s, b, S128); }
  { cuuint64_t d[3] = {512, 64, 32}, s[2] = {1024, 65536}; cuuint32_t b[3] = {64, 64, 2}; encode(enc, &mp.t, pT, 3, d, s, b, S128); }
  { cuuint64_t d[2] = {64, 4096}, s[1] = {128}; cuuint32_t b[2] = {64, 64}; encode(enc, &mp.e, pET, 2, d, s, b, S128); }
  { cuuint64_t d[2] = {1792, 512}, s[1] = {3584}; cuuint32_t b[2] = {64, 64}, b2[2] = {32, 128};
    encode(enc, &mp.g64, Wg, 2, d, s, b, S128); encode(enc, &mp.u64, Wu, 2, d, s, b, S128);
    encode(enc, &mp.g32, Wg, 2, d, s, b2, S64); encode(enc, &mp.u32, Wu, 2, d, s, b2, S64); }
  { cuuint64_t d[2] = {512, 1792}, s[1] = {1024}; cuuint32_t b[2] = {64, 224}; encode(enc, &mp.d224, Wd, 2, d, s, b, S128); }
  { cuuint64_t d[4] = {264, 32, 8, 8}, s[3] = {32896, 512, 4112}; cuuint32_t b[4] = {48, 32, 1, 1};
    encode(enc, &mp.wr, w_r, 4, d, s, b, CU_TENSOR_MAP_SWIZZLE_NONE); encode(enc, &mp.wi, w_i, 4, d, s, b, CU_TENSOR_MAP_SWIZZLE_NONE); }

  cudaFuncSetAttribute(fused_kernel, cudaFuncAttributeMaxDynamicSharedMemorySize, SMEM_BYTES);
  fused_kernel<<<NCTA, 512, SMEM_BYTES>>>((Work*)pW, (const uint16_t*)pDT, w_r, w_i, gw, x, (__nv_bfloat16*)d_out, mp);
}
```

```cpp
#include <cuda_runtime.h>
#include <cuda_bf16.h>
#include <cuda.h>
#include <stdint.h>

namespace tbl {
constexpr double PI = 3.14159265358979323846264338327950288;
constexpr double sin_s(double x) { double t = x, s = x; for (int n = 1; n < 12; n++) { t *= -x * x / ((2 * n) * (2 * n + 1)); s += t; } return s; }
constexpr double cos_s(double x) { double t = 1, s = 1; for (int n = 1; n < 12; n++) { t *= -x * x / ((2 * n - 1) * (2 * n)); s += t; } return s; }
constexpr double cos2048(int m) {
  m &= 2047; if (m > 1024) m = 2048 - m;
  bool neg = false; if (m > 512) { m = 1024 - m; neg = true; }
  double v = (m <= 256) ? cos_s(2 * PI * m / 2048) : sin_s(2 * PI * (512 - m) / 2048);
  return neg ? -v : v;
}
constexpr uint16_t to_bf16(double v) {
  if (v == 0) return 0;
  uint16_t s = 0; if (v < 0) { s = 0x8000; v = -v; }
  int e = 0; while (v >= 2) { v /= 2; e++; } while (v < 1) { v *= 2; e--; }
  double m = (v - 1) * 128; int mi = (int)m; double fr = m - mi;
  if (fr > 0.5 || (fr == 0.5 && (mi & 1))) mi++;
  if (mi == 128) { mi = 0; e++; }
  return (uint16_t)(s | ((e + 127) << 7) | mi);
}
struct CosT { uint16_t v[2048]; constexpr CosT() : v() { for (int i = 0; i < 2048; i++) v[i] = to_bf16(cos2048(i)); } };
struct alignas(1024) FT {
  uint16_t v[512 * 512];
  constexpr FT() : v() {
    CosT c;
    for (int r = 0; r < 512; r++) {
      int k = (r >> 5) * 16 + 2 * (r & 7) + ((r >> 4) & 1), e = (r >> 3) & 1;
      int mul = 4 * k, add = e ? 512 : 0;
      if (k == 0 && e == 1) { mul = 1024; add = 0; }
      for (int d = 0; d < 512; d++) v[r * 512 + d] = c.v[(d * mul + add) & 2047];
    }
  }
};
struct alignas(1024) ET {
  uint16_t v[2048 * 128];
  constexpr ET() : v() {
    CosT c;
    for (int s = 0; s < 2048; s++)
      for (int j = 0; j < 64; j++) {
        const int o = (s & 31) * 8192 + (s >> 5) * 64 + j;
        v[o] = c.v[(s * j) & 2047]; v[o + 4096] = c.v[(s * j + 512) & 2047];
      }
  }
};
struct alignas(1024) DT {
  uint16_t v[64 * 64];
  constexpr DT() : v() {
    CosT c;
    for (int r = 0; r < 64; r++)
      for (int n = 0; n < 64; n++) {
        const int sg = r >> 1, s0 = (sg & ~6) | ((sg & 2) << 1) | ((sg & 4) >> 1), e = r & 1, f = n & 1;
        const int m = 64 * s0 * (n >> 1) + (e == f ? 0 : e ? -512 : 512);
        v[r * 64 + (((n >> 3) ^ (r & 7)) << 3) + (n & 7)] = c.v[m & 2047];
      }
  }
};
}

__device__ constexpr tbl::FT g_FT = tbl::FT();
__device__ constexpr tbl::ET g_ET = tbl::ET();
__device__ constexpr tbl::DT g_DT = tbl::DT();

struct alignas(1024) Work {
  unsigned epoch[132 * 8];
  unsigned cntX[8 * 32], cntT[8 * 32], cntP[128 * 32], cntW[32], cntH[32];
  alignas(16) float gate[16 * 128];
  alignas(16) uint2 Wh[2 * 2048];
  alignas(16) uint2 Ts[32 * 64];
  alignas(1024) uint16_t X[129 * 8192];
  alignas(1024) uint16_t T[32 * 64 * 512];
  alignas(1024) uint4 part[128 * 3 * 1024];
};
__device__ Work g_work;
#define PROF_EV(i) do {} while (0)
#define PROF_CK(i) do {} while (0)

__device__ __forceinline__ uint32_t smem_u32(const void* p) { return (uint32_t)__cvta_generic_to_shared(p); }
__device__ __forceinline__ void mbar_init(uint32_t bar, uint32_t cnt) { asm volatile("mbarrier.init.shared::cta.b64 [%0], %1;" ::"r"(bar), "r"(cnt)); }
__device__ __forceinline__ void mbar_expect_tx(uint32_t bar, uint32_t bytes) { asm volatile("mbarrier.arrive.expect_tx.shared::cta.b64 _, [%0], %1;" ::"r"(bar), "r"(bytes) : "memory"); }
__device__ __forceinline__ void mbar_arrive(uint32_t bar) { asm volatile("mbarrier.arrive.shared::cta.b64 _, [%0];" ::"r"(bar) : "memory"); }
__device__ __forceinline__ bool elect_one() {
  uint32_t p;
  asm volatile("{\n.reg .pred p;\nelect.sync _|p, 0xffffffff;\nselp.u32 %0, 1, 0, p;\n}" : "=r"(p));
  return p;
}
__device__ __forceinline__ void mbar_arrive_if(bool p, uint32_t bar) {
  asm volatile("{\n.reg .pred p;\nsetp.ne.b32 p, %1, 0;\n@p mbarrier.arrive.shared::cta.b64 _, [%0];\n}" ::"r"(bar), "r"((int)p) : "memory");
}
__device__ __forceinline__ void hint_add_if(bool p, unsigned* a) {
  asm volatile("{\n.reg .pred p;\nsetp.ne.b32 p, %1, 0;\n@p red.relaxed.gpu.global.add.u32 [%0], 1;\n}" ::"l"(a), "r"((int)p) : "memory");
}
__device__ __forceinline__ bool mbar_try(uint32_t bar, uint32_t parity) {
  uint32_t ok;
  asm volatile("{\n.reg .pred p;\nmbarrier.test_wait.parity.shared::cta.b64 p, [%1], %2;\nselp.u32 %0, 1, 0, p;\n}" : "=r"(ok) : "r"(bar), "r"(parity) : "memory");
  return ok;
}
__device__ __forceinline__ void mbar_wait(uint32_t bar, uint32_t parity) {
  asm volatile(
      "{\n.reg .pred p;\n.reg .u32 n;\nmov.u32 n, 0;\n"
      "W_LOOP:\nmbarrier.try_wait.parity.shared::cta.b64 p, [%0], %1;\n@p bra W_DONE;\n"
      "add.u32 n, n, 1;\nsetp.lt.u32 p, n, 0x40000;\n@p bra W_LOOP;\ntrap;\nW_DONE:\n}" ::"r"(bar), "r"(parity) : "memory");
}
__device__ __forceinline__ void bulk_load(uint32_t dst, const void* src, uint32_t bytes, uint32_t bar) {
  asm volatile("cp.async.bulk.shared::cluster.global.mbarrier::complete_tx::bytes [%0], [%1], %2, [%3];" ::"r"(dst), "l"(src), "r"(bytes), "r"(bar) : "memory");
}
__device__ __forceinline__ void spin_guard(uint32_t t0) { if ((uint32_t)clock() - t0 > (1u << 30)) __trap(); }
__device__ __forceinline__ float2 ld_x2(const float2* p) { float2 v; asm volatile("ld.relaxed.gpu.global.v2.f32 {%0,%1}, [%2];" : "=f"(v.x), "=f"(v.y) : "l"(p) : "memory"); return v; }
__device__ __forceinline__ void st_u2(uint2* p, uint32_t a, uint32_t b) { asm volatile("st.relaxed.gpu.global.v2.u32 [%0], {%1,%2};" ::"l"(p), "r"(a), "r"(b) : "memory"); }
__device__ __forceinline__ uint32_t ld_x1(const void* p) { uint32_t v; asm volatile("ld.relaxed.gpu.global.u32 %0, [%1];" : "=r"(v) : "l"(p) : "memory"); return v; }
__device__ __forceinline__ uint4 ld_x4(const void* p) { uint4 v; asm volatile("ld.relaxed.gpu.global.v4.u32 {%0,%1,%2,%3}, [%4];" : "=r"(v.x), "=r"(v.y), "=r"(v.z), "=r"(v.w) : "l"(p) : "memory"); return v; }
__device__ __forceinline__ uint32_t mapa(uint32_t a, uint32_t cta) { uint32_t r; asm volatile("mapa.shared::cluster.u32 %0, %1, %2;" : "=r"(r) : "r"(a), "r"(cta)); return r; }
__device__ __forceinline__ void stsm4t(uint32_t a, uint32_t r0, uint32_t r1, uint32_t r2, uint32_t r3) {
  asm volatile("stmatrix.sync.aligned.m8n8.x4.trans.shared.b16 [%0], {%1,%2,%3,%4};" ::"r"(a), "r"(r0), "r"(r1), "r"(r2), "r"(r3) : "memory");
}
__device__ __forceinline__ void hint_add(unsigned* p) { asm volatile("red.relaxed.gpu.global.add.u32 [%0], 1;" ::"l"(p) : "memory"); }
__device__ __forceinline__ void hint_wait(const unsigned* p, unsigned target) {
  const uint32_t t0 = (uint32_t)clock();
  while ((int)(ld_x1(p) - target) < 0) spin_guard(t0);
}
__device__ __forceinline__ void bulk_done_signal(unsigned* p) {
  asm volatile("cp.async.bulk.commit_group;\ncp.async.bulk.wait_group 0;\nfence.proxy.async.global;" ::: "memory");
  hint_add(p);
}
__device__ __forceinline__ void flag_wait(const unsigned* p, unsigned target) {
  hint_wait(p, target);
  asm volatile("fence.proxy.async.global;" ::: "memory");
}
__device__ __forceinline__ void tma2d(uint32_t dst, const CUtensorMap* m, uint32_t bar, int c0, int c1) {
  asm volatile("cp.async.bulk.tensor.2d.shared::cluster.global.mbarrier::complete_tx::bytes [%0], [%1, {%3, %4}], [%2];" ::"r"(dst), "l"(m), "r"(bar), "r"(c0), "r"(c1) : "memory");
}
__device__ __forceinline__ void tma3d(uint32_t dst, const CUtensorMap* m, uint32_t bar, int c0, int c1, int c2) {
  asm volatile("cp.async.bulk.tensor.3d.shared::cluster.global.mbarrier::complete_tx::bytes [%0], [%1, {%3, %4, %5}], [%2];" ::"r"(dst), "l"(m), "r"(bar), "r"(c0), "r"(c1), "r"(c2) : "memory");
}
__device__ __forceinline__ void tma4d(uint32_t dst, const CUtensorMap* m, uint32_t bar, int c0, int c1, int c2, int c3) {
  asm volatile("cp.async.bulk.tensor.4d.shared::cluster.global.mbarrier::complete_tx::bytes [%0], [%1, {%3, %4, %5, %6}], [%2];" ::"r"(dst), "l"(m), "r"(bar), "r"(c0), "r"(c1), "r"(c2), "r"(c3) : "memory");
}
__device__ __forceinline__ void wg_fence() { asm volatile("wgmma.fence.sync.aligned;" ::: "memory"); }
__device__ __forceinline__ void wg_commit() { asm volatile("wgmma.commit_group.sync.aligned;" ::: "memory"); }
template <int N> __device__ __forceinline__ void wg_wait() { asm volatile("wgmma.wait_group.sync.aligned %0;" ::"n"(N) : "memory"); }
template <int O, int N, int NN> __device__ __forceinline__ void fence_regs(float (&d)[NN]) {
#pragma unroll
  for (int i = 0; i < N; i++) asm volatile("" : "+f"(d[O + i])::"memory");
}
__device__ __forceinline__ uint32_t pack_bf16(float lo, float hi) {
  uint32_t r; asm("cvt.rn.bf16x2.f32 %0, %1, %2;" : "=r"(r) : "f"(hi), "f"(lo)); return r;
}
__device__ __forceinline__ uint32_t pack_pin(float lo, float hi) {
  uint32_t r; asm volatile("cvt.rn.bf16x2.f32 %0, %1, %2;" : "=r"(r) : "f"(hi), "f"(lo) : "memory"); return r;
}
__device__ __forceinline__ uint32_t add_bf2(uint32_t a, uint32_t b) { uint32_t r; asm("add.rn.bf16x2 %0, %1, %2;" : "=r"(r) : "r"(a), "r"(b)); return r; }
__device__ __forceinline__ float bf_lo(uint32_t u) { return __uint_as_float(u << 16); }
__device__ __forceinline__ float bf_hi(uint32_t u) { return __uint_as_float(u & 0xffff0000u); }

__device__ __forceinline__ uint64_t d128(uint32_t lo) { uint64_t d; asm("mov.b64 %0, {%1, 0x40000040};" : "=l"(d) : "r"(lo)); return d; }
__device__ __forceinline__ uint64_t d64(uint32_t lo) { uint64_t d; asm("mov.b64 %0, {%1, 0x80000020};" : "=l"(d) : "r"(lo)); return d; }
template<int O,int TB,int ACC,int NN> __device__ __forceinline__ void mma_ss64(float (&d)[NN], uint64_t da, uint64_t db, int sd = 0){
  if constexpr (ACC == 1) asm volatile("wgmma.mma_async.sync.aligned.m64n64k16.f32.bf16.bf16 {%0,%1,%2,%3,%4,%5,%6,%7,%8,%9,%10,%11,%12,%13,%14,%15,%16,%17,%18,%19,%20,%21,%22,%23,%24,%25,%26,%27,%28,%29,%30,%31}, %32, %33, 1, 1, 1, %35, %34;"
   : "+f"(d[O+0]), "+f"(d[O+1]), "+f"(d[O+2]), "+f"(d[O+3]), "+f"(d[O+4]), "+f"(d[O+5]), "+f"(d[O+6]), "+f"(d[O+7]), "+f"(d[O+8]), "+f"(d[O+9]), "+f"(d[O+10]), "+f"(d[O+11]), "+f"(d[O+12]), "+f"(d[O+13]), "+f"(d[O+14]), "+f"(d[O+15]), "+f"(d[O+16]), "+f"(d[O+17]), "+f"(d[O+18]), "+f"(d[O+19]), "+f"(d[O+20]), "+f"(d[O+21]), "+f"(d[O+22]), "+f"(d[O+23]), "+f"(d[O+24]), "+f"(d[O+25]), "+f"(d[O+26]), "+f"(d[O+27]), "+f"(d[O+28]), "+f"(d[O+29]), "+f"(d[O+30]), "+f"(d[O+31])
   : "l"(da), "l"(db), "n"(TB & 1), "n"(TB >> 1));
  else if constexpr (ACC == 0) asm volatile("wgmma.mma_async.sync.aligned.m64n64k16.f32.bf16.bf16 {%0,%1,%2,%3,%4,%5,%6,%7,%8,%9,%10,%11,%12,%13,%14,%15,%16,%17,%18,%19,%20,%21,%22,%23,%24,%25,%26,%27,%28,%29,%30,%31}, %32, %33, 0, 1, 1, %35, %34;"
   : "=f"(d[O+0]), "=f"(d[O+1]), "=f"(d[O+2]), "=f"(d[O+3]), "=f"(d[O+4]), "=f"(d[O+5]), "=f"(d[O+6]), "=f"(d[O+7]), "=f"(d[O+8]), "=f"(d[O+9]), "=f"(d[O+10]), "=f"(d[O+11]), "=f"(d[O+12]), "=f"(d[O+13]), "=f"(d[O+14]), "=f"(d[O+15]), "=f"(d[O+16]), "=f"(d[O+17]), "=f"(d[O+18]), "=f"(d[O+19]), "=f"(d[O+20]), "=f"(d[O+21]), "=f"(d[O+22]), "=f"(d[O+23]), "=f"(d[O+24]), "=f"(d[O+25]), "=f"(d[O+26]), "=f"(d[O+27]), "=f"(d[O+28]), "=f"(d[O+29]), "=f"(d[O+30]), "=f"(d[O+31])
   : "l"(da), "l"(db), "n"(TB & 1), "n"(TB >> 1));
  else asm volatile("{\n.reg .pred p;\nsetp.ne.b32 p, %36, 0;\nwgmma.mma_async.sync.aligned.m64n64k16.f32.bf16.bf16 {%0,%1,%2,%3,%4,%5,%6,%7,%8,%9,%10,%11,%12,%13,%14,%15,%16,%17,%18,%19,%20,%21,%22,%23,%24,%25,%26,%27,%28,%29,%30,%31}, %32, %33, p, 1, 1, %35, %34;\n}"
   : "+f"(d[O+0]), "+f"(d[O+1]), "+f"(d[O+2]), "+f"(d[O+3]), "+f"(d[O+4]), "+f"(d[O+5]), "+f"(d[O+6]), "+f"(d[O+7]), "+f"(d[O+8]), "+f"(d[O+9]), "+f"(d[O+10]), "+f"(d[O+11]), "+f"(d[O+12]), "+f"(d[O+13]), "+f"(d[O+14]), "+f"(d[O+15]), "+f"(d[O+16]), "+f"(d[O+17]), "+f"(d[O+18]), "+f"(d[O+19]), "+f"(d[O+20]), "+f"(d[O+21]), "+f"(d[O+22]), "+f"(d[O+23]), "+f"(d[O+24]), "+f"(d[O+25]), "+f"(d[O+26]), "+f"(d[O+27]), "+f"(d[O+28]), "+f"(d[O+29]), "+f"(d[O+30]), "+f"(d[O+31])
   : "l"(da), "l"(db), "n"(TB & 1), "n"(TB >> 1), "r"(sd));
}
template<int O,int TB,int ACC,int NN> __device__ __forceinline__ void mma_rs64(float (&d)[NN], uint32_t a0, uint32_t a1, uint32_t a2, uint32_t a3, uint64_t db, int sd = 0){
  if constexpr (ACC == 1) asm volatile("wgmma.mma_async.sync.aligned.m64n64k16.f32.bf16.bf16 {%0,%1,%2,%3,%4,%5,%6,%7,%8,%9,%10,%11,%12,%13,%14,%15,%16,%17,%18,%19,%20,%21,%22,%23,%24,%25,%26,%27,%28,%29,%30,%31}, {%32,%33,%34,%35}, %36, 1, 1, 1, %37;"
   : "+f"(d[O+0]), "+f"(d[O+1]), "+f"(d[O+2]), "+f"(d[O+3]), "+f"(d[O+4]), "+f"(d[O+5]), "+f"(d[O+6]), "+f"(d[O+7]), "+f"(d[O+8]), "+f"(d[O+9]), "+f"(d[O+10]), "+f"(d[O+11]), "+f"(d[O+12]), "+f"(d[O+13]), "+f"(d[O+14]), "+f"(d[O+15]), "+f"(d[O+16]), "+f"(d[O+17]), "+f"(d[O+18]), "+f"(d[O+19]), "+f"(d[O+20]), "+f"(d[O+21]), "+f"(d[O+22]), "+f"(d[O+23]), "+f"(d[O+24]), "+f"(d[O+25]), "+f"(d[O+26]), "+f"(d[O+27]), "+f"(d[O+28]), "+f"(d[O+29]), "+f"(d[O+30]), "+f"(d[O+31])
   : "r"(a0), "r"(a1), "r"(a2), "r"(a3), "l"(db), "n"(TB));
  else if constexpr (ACC == 0) asm volatile("wgmma.mma_async.sync.aligned.m64n64k16.f32.bf16.bf16 {%0,%1,%2,%3,%4,%5,%6,%7,%8,%9,%10,%11,%12,%13,%14,%15,%16,%17,%18,%19,%20,%21,%22,%23,%24,%25,%26,%27,%28,%29,%30,%31}, {%32,%33,%34,%35}, %36, 0, 1, 1, %37;"
   : "=f"(d[O+0]), "=f"(d[O+1]), "=f"(d[O+2]), "=f"(d[O+3]), "=f"(d[O+4]), "=f"(d[O+5]), "=f"(d[O+6]), "=f"(d[O+7]), "=f"(d[O+8]), "=f"(d[O+9]), "=f"(d[O+10]), "=f"(d[O+11]), "=f"(d[O+12]), "=f"(d[O+13]), "=f"(d[O+14]), "=f"(d[O+15]), "=f"(d[O+16]), "=f"(d[O+17]), "=f"(d[O+18]), "=f"(d[O+19]), "=f"(d[O+20]), "=f"(d[O+21]), "=f"(d[O+22]), "=f"(d[O+23]), "=f"(d[O+24]), "=f"(d[O+25]), "=f"(d[O+26]), "=f"(d[O+27]), "=f"(d[O+28]), "=f"(d[O+29]), "=f"(d[O+30]), "=f"(d[O+31])
   : "r"(a0), "r"(a1), "r"(a2), "r"(a3), "l"(db), "n"(TB));
  else asm volatile("{\n.reg .pred p;\nsetp.ne.b32 p, %38, 0;\nwgmma.mma_async.sync.aligned.m64n64k16.f32.bf16.bf16 {%0,%1,%2,%3,%4,%5,%6,%7,%8,%9,%10,%11,%12,%13,%14,%15,%16,%17,%18,%19,%20,%21,%22,%23,%24,%25,%26,%27,%28,%29,%30,%31}, {%32,%33,%34,%35}, %36, p, 1, 1, %37;\n}"
   : "+f"(d[O+0]), "+f"(d[O+1]), "+f"(d[O+2]), "+f"(d[O+3]), "+f"(d[O+4]), "+f"(d[O+5]), "+f"(d[O+6]), "+f"(d[O+7]), "+f"(d[O+8]), "+f"(d[O+9]), "+f"(d[O+10]), "+f"(d[O+11]), "+f"(d[O+12]), "+f"(d[O+13]), "+f"(d[O+14]), "+f"(d[O+15]), "+f"(d[O+16]), "+f"(d[O+17]), "+f"(d[O+18]), "+f"(d[O+19]), "+f"(d[O+20]), "+f"(d[O+21]), "+f"(d[O+22]), "+f"(d[O+23]), "+f"(d[O+24]), "+f"(d[O+25]), "+f"(d[O+26]), "+f"(d[O+27]), "+f"(d[O+28]), "+f"(d[O+29]), "+f"(d[O+30]), "+f"(d[O+31])
   : "r"(a0), "r"(a1), "r"(a2), "r"(a3), "l"(db), "n"(TB), "r"(sd));
}
template<int O,int TB,int ACC,int NN> __device__ __forceinline__ void mma_ss128(float (&d)[NN], uint64_t da, uint64_t db, int sd = 0){
  if constexpr (ACC == 1) asm volatile("wgmma.mma_async.sync.aligned.m64n128k16.f32.bf16.bf16 {%0,%1,%2,%3,%4,%5,%6,%7,%8,%9,%10,%11,%12,%13,%14,%15,%16,%17,%18,%19,%20,%21,%22,%23,%24,%25,%26,%27,%28,%29,%30,%31,%32,%33,%34,%35,%36,%37,%38,%39,%40,%41,%42,%43,%44,%45,%46,%47,%48,%49,%50,%51,%52,%53,%54,%55,%56,%57,%58,%59,%60,%61,%62,%63}, %64, %65, 1, 1, 1, %67, %66;"
   : "+f"(d[O+0]), "+f"(d[O+1]), "+f"(d[O+2]), "+f"(d[O+3]), "+f"(d[O+4]), "+f"(d[O+5]), "+f"(d[O+6]), "+f"(d[O+7]), "+f"(d[O+8]), "+f"(d[O+9]), "+f"(d[O+10]), "+f"(d[O+11]), "+f"(d[O+12]), "+f"(d[O+13]), "+f"(d[O+14]), "+f"(d[O+15]), "+f"(d[O+16]), "+f"(d[O+17]), "+f"(d[O+18]), "+f"(d[O+19]), "+f"(d[O+20]), "+f"(d[O+21]), "+f"(d[O+22]), "+f"(d[O+23]), "+f"(d[O+24]), "+f"(d[O+25]), "+f"(d[O+26]), "+f"(d[O+27]), "+f"(d[O+28]), "+f"(d[O+29]), "+f"(d[O+30]), "+f"(d[O+31]), "+f"(d[O+32]), "+f"(d[O+33]), "+f"(d[O+34]), "+f"(d[O+35]), "+f"(d[O+36]), "+f"(d[O+37]), "+f"(d[O+38]), "+f"(d[O+39]), "+f"(d[O+40]), "+f"(d[O+41]), "+f"(d[O+42]), "+f"(d[O+43]), "+f"(d[O+44]), "+f"(d[O+45]), "+f"(d[O+46]), "+f"(d[O+47]), "+f"(d[O+48]), "+f"(d[O+49]), "+f"(d[O+50]), "+f"(d[O+51]), "+f"(d[O+52]), "+f"(d[O+53]), "+f"(d[O+54]), "+f"(d[O+55]), "+f"(d[O+56]), "+f"(d[O+57]), "+f"(d[O+58]), "+f"(d[O+59]), "+f"(d[O+60]), "+f"(d[O+61]), "+f"(d[O+62]), "+f"(d[O+63])
   : "l"(da), "l"(db), "n"(TB & 1), "n"(TB >> 1));
  else if constexpr (ACC == 0) asm volatile("wgmma.mma_async.sync.aligned.m64n128k16.f32.bf16.bf16 {%0,%1,%2,%3,%4,%5,%6,%7,%8,%9,%10,%11,%12,%13,%14,%15,%16,%17,%18,%19,%20,%21,%22,%23,%24,%25,%26,%27,%28,%29,%30,%31,%32,%33,%34,%35,%36,%37,%38,%39,%40,%41,%42,%43,%44,%45,%46,%47,%48,%49,%50,%51,%52,%53,%54,%55,%56,%57,%58,%59,%60,%61,%62,%63}, %64, %65, 0, 1, 1, %67, %66;"
   : "=f"(d[O+0]), "=f"(d[O+1]), "=f"(d[O+2]), "=f"(d[O+3]), "=f"(d[O+4]), "=f"(d[O+5]), "=f"(d[O+6]), "=f"(d[O+7]), "=f"(d[O+8]), "=f"(d[O+9]), "=f"(d[O+10]), "=f"(d[O+11]), "=f"(d[O+12]), "=f"(d[O+13]), "=f"(d[O+14]), "=f"(d[O+15]), "=f"(d[O+16]), "=f"(d[O+17]), "=f"(d[O+18]), "=f"(d[O+19]), "=f"(d[O+20]), "=f"(d[O+21]), "=f"(d[O+22]), "=f"(d[O+23]), "=f"(d[O+24]), "=f"(d[O+25]), "=f"(d[O+26]), "=f"(d[O+27]), "=f"(d[O+28]), "=f"(d[O+29]), "=f"(d[O+30]), "=f"(d[O+31]), "=f"(d[O+32]), "=f"(d[O+33]), "=f"(d[O+34]), "=f"(d[O+35]), "=f"(d[O+36]), "=f"(d[O+37]), "=f"(d[O+38]), "=f"(d[O+39]), "=f"(d[O+40]), "=f"(d[O+41]), "=f"(d[O+42]), "=f"(d[O+43]), "=f"(d[O+44]), "=f"(d[O+45]), "=f"(d[O+46]), "=f"(d[O+47]), "=f"(d[O+48]), "=f"(d[O+49]), "=f"(d[O+50]), "=f"(d[O+51]), "=f"(d[O+52]), "=f"(d[O+53]), "=f"(d[O+54]), "=f"(d[O+55]), "=f"(d[O+56]), "=f"(d[O+57]), "=f"(d[O+58]), "=f"(d[O+59]), "=f"(d[O+60]), "=f"(d[O+61]), "=f"(d[O+62]), "=f"(d[O+63])
   : "l"(da), "l"(db), "n"(TB & 1), "n"(TB >> 1));
  else asm volatile("{\n.reg .pred p;\nsetp.ne.b32 p, %68, 0;\nwgmma.mma_async.sync.aligned.m64n128k16.f32.bf16.bf16 {%0,%1,%2,%3,%4,%5,%6,%7,%8,%9,%10,%11,%12,%13,%14,%15,%16,%17,%18,%19,%20,%21,%22,%23,%24,%25,%26,%27,%28,%29,%30,%31,%32,%33,%34,%35,%36,%37,%38,%39,%40,%41,%42,%43,%44,%45,%46,%47,%48,%49,%50,%51,%52,%53,%54,%55,%56,%57,%58,%59,%60,%61,%62,%63}, %64, %65, p, 1, 1, %67, %66;\n}"
   : "+f"(d[O+0]), "+f"(d[O+1]), "+f"(d[O+2]), "+f"(d[O+3]), "+f"(d[O+4]), "+f"(d[O+5]), "+f"(d[O+6]), "+f"(d[O+7]), "+f"(d[O+8]), "+f"(d[O+9]), "+f"(d[O+10]), "+f"(d[O+11]), "+f"(d[O+12]), "+f"(d[O+13]), "+f"(d[O+14]), "+f"(d[O+15]), "+f"(d[O+16]), "+f"(d[O+17]), "+f"(d[O+18]), "+f"(d[O+19]), "+f"(d[O+20]), "+f"(d[O+21]), "+f"(d[O+22]), "+f"(d[O+23]), "+f"(d[O+24]), "+f"(d[O+25]), "+f"(d[O+26]), "+f"(d[O+27]), "+f"(d[O+28]), "+f"(d[O+29]), "+f"(d[O+30]), "+f"(d[O+31]), "+f"(d[O+32]), "+f"(d[O+33]), "+f"(d[O+34]), "+f"(d[O+35]), "+f"(d[O+36]), "+f"(d[O+37]), "+f"(d[O+38]), "+f"(d[O+39]), "+f"(d[O+40]), "+f"(d[O+41]), "+f"(d[O+42]), "+f"(d[O+43]), "+f"(d[O+44]), "+f"(d[O+45]), "+f"(d[O+46]), "+f"(d[O+47]), "+f"(d[O+48]), "+f"(d[O+49]), "+f"(d[O+50]), "+f"(d[O+51]), "+f"(d[O+52]), "+f"(d[O+53]), "+f"(d[O+54]), "+f"(d[O+55]), "+f"(d[O+56]), "+f"(d[O+57]), "+f"(d[O+58]), "+f"(d[O+59]), "+f"(d[O+60]), "+f"(d[O+61]), "+f"(d[O+62]), "+f"(d[O+63])
   : "l"(da), "l"(db), "n"(TB & 1), "n"(TB >> 1), "r"(sd));
}
template<int O,int TB,int ACC,int NN> __device__ __forceinline__ void mma_rs128(float (&d)[NN], uint32_t a0, uint32_t a1, uint32_t a2, uint32_t a3, uint64_t db, int sd = 0){
  if constexpr (ACC == 1) asm volatile("wgmma.mma_async.sync.aligned.m64n128k16.f32.bf16.bf16 {%0,%1,%2,%3,%4,%5,%6,%7,%8,%9,%10,%11,%12,%13,%14,%15,%16,%17,%18,%19,%20,%21,%22,%23,%24,%25,%26,%27,%28,%29,%30,%31,%32,%33,%34,%35,%36,%37,%38,%39,%40,%41,%42,%43,%44,%45,%46,%47,%48,%49,%50,%51,%52,%53,%54,%55,%56,%57,%58,%59,%60,%61,%62,%63}, {%64,%65,%66,%67}, %68, 1, 1, 1, %69;"
   : "+f"(d[O+0]), "+f"(d[O+1]), "+f"(d[O+2]), "+f"(d[O+3]), "+f"(d[O+4]), "+f"(d[O+5]), "+f"(d[O+6]), "+f"(d[O+7]), "+f"(d[O+8]), "+f"(d[O+9]), "+f"(d[O+10]), "+f"(d[O+11]), "+f"(d[O+12]), "+f"(d[O+13]), "+f"(d[O+14]), "+f"(d[O+15]), "+f"(d[O+16]), "+f"(d[O+17]), "+f"(d[O+18]), "+f"(d[O+19]), "+f"(d[O+20]), "+f"(d[O+21]), "+f"(d[O+22]), "+f"(d[O+23]), "+f"(d[O+24]), "+f"(d[O+25]), "+f"(d[O+26]), "+f"(d[O+27]), "+f"(d[O+28]), "+f"(d[O+29]), "+f"(d[O+30]), "+f"(d[O+31]), "+f"(d[O+32]), "+f"(d[O+33]), "+f"(d[O+34]), "+f"(d[O+35]), "+f"(d[O+36]), "+f"(d[O+37]), "+f"(d[O+38]), "+f"(d[O+39]), "+f"(d[O+40]), "+f"(d[O+41]), "+f"(d[O+42]), "+f"(d[O+43]), "+f"(d[O+44]), "+f"(d[O+45]), "+f"(d[O+46]), "+f"(d[O+47]), "+f"(d[O+48]), "+f"(d[O+49]), "+f"(d[O+50]), "+f"(d[O+51]), "+f"(d[O+52]), "+f"(d[O+53]), "+f"(d[O+54]), "+f"(d[O+55]), "+f"(d[O+56]), "+f"(d[O+57]), "+f"(d[O+58]), "+f"(d[O+59]), "+f"(d[O+60]), "+f"(d[O+61]), "+f"(d[O+62]), "+f"(d[O+63])
   : "r"(a0), "r"(a1), "r"(a2), "r"(a3), "l"(db), "n"(TB));
  else if constexpr (ACC == 0) asm volatile("wgmma.mma_async.sync.aligned.m64n128k16.f32.bf16.bf16 {%0,%1,%2,%3,%4,%5,%6,%7,%8,%9,%10,%11,%12,%13,%14,%15,%16,%17,%18,%19,%20,%21,%22,%23,%24,%25,%26,%27,%28,%29,%30,%31,%32,%33,%34,%35,%36,%37,%38,%39,%40,%41,%42,%43,%44,%45,%46,%47,%48,%49,%50,%51,%52,%53,%54,%55,%56,%57,%58,%59,%60,%61,%62,%63}, {%64,%65,%66,%67}, %68, 0, 1, 1, %69;"
   : "=f"(d[O+0]), "=f"(d[O+1]), "=f"(d[O+2]), "=f"(d[O+3]), "=f"(d[O+4]), "=f"(d[O+5]), "=f"(d[O+6]), "=f"(d[O+7]), "=f"(d[O+8]), "=f"(d[O+9]), "=f"(d[O+10]), "=f"(d[O+11]), "=f"(d[O+12]), "=f"(d[O+13]), "=f"(d[O+14]), "=f"(d[O+15]), "=f"(d[O+16]), "=f"(d[O+17]), "=f"(d[O+18]), "=f"(d[O+19]), "=f"(d[O+20]), "=f"(d[O+21]), "=f"(d[O+22]), "=f"(d[O+23]), "=f"(d[O+24]), "=f"(d[O+25]), "=f"(d[O+26]), "=f"(d[O+27]), "=f"(d[O+28]), "=f"(d[O+29]), "=f"(d[O+30]), "=f"(d[O+31]), "=f"(d[O+32]), "=f"(d[O+33]), "=f"(d[O+34]), "=f"(d[O+35]), "=f"(d[O+36]), "=f"(d[O+37]), "=f"(d[O+38]), "=f"(d[O+39]), "=f"(d[O+40]), "=f"(d[O+41]), "=f"(d[O+42]), "=f"(d[O+43]), "=f"(d[O+44]), "=f"(d[O+45]), "=f"(d[O+46]), "=f"(d[O+47]), "=f"(d[O+48]), "=f"(d[O+49]), "=f"(d[O+50]), "=f"(d[O+51]), "=f"(d[O+52]), "=f"(d[O+53]), "=f"(d[O+54]), "=f"(d[O+55]), "=f"(d[O+56]), "=f"(d[O+57]), "=f"(d[O+58]), "=f"(d[O+59]), "=f"(d[O+60]), "=f"(d[O+61]), "=f"(d[O+62]), "=f"(d[O+63])
   : "r"(a0), "r"(a1), "r"(a2), "r"(a3), "l"(db), "n"(TB));
  else asm volatile("{\n.reg .pred p;\nsetp.ne.b32 p, %70, 0;\nwgmma.mma_async.sync.aligned.m64n128k16.f32.bf16.bf16 {%0,%1,%2,%3,%4,%5,%6,%7,%8,%9,%10,%11,%12,%13,%14,%15,%16,%17,%18,%19,%20,%21,%22,%23,%24,%25,%26,%27,%28,%29,%30,%31,%32,%33,%34,%35,%36,%37,%38,%39,%40,%41,%42,%43,%44,%45,%46,%47,%48,%49,%50,%51,%52,%53,%54,%55,%56,%57,%58,%59,%60,%61,%62,%63}, {%64,%65,%66,%67}, %68, p, 1, 1, %69;\n}"
   : "+f"(d[O+0]), "+f"(d[O+1]), "+f"(d[O+2]), "+f"(d[O+3]), "+f"(d[O+4]), "+f"(d[O+5]), "+f"(d[O+6]), "+f"(d[O+7]), "+f"(d[O+8]), "+f"(d[O+9]), "+f"(d[O+10]), "+f"(d[O+11]), "+f"(d[O+12]), "+f"(d[O+13]), "+f"(d[O+14]), "+f"(d[O+15]), "+f"(d[O+16]), "+f"(d[O+17]), "+f"(d[O+18]), "+f"(d[O+19]), "+f"(d[O+20]), "+f"(d[O+21]), "+f"(d[O+22]), "+f"(d[O+23]), "+f"(d[O+24]), "+f"(d[O+25]), "+f"(d[O+26]), "+f"(d[O+27]), "+f"(d[O+28]), "+f"(d[O+29]), "+f"(d[O+30]), "+f"(d[O+31]), "+f"(d[O+32]), "+f"(d[O+33]), "+f"(d[O+34]), "+f"(d[O+35]), "+f"(d[O+36]), "+f"(d[O+37]), "+f"(d[O+38]), "+f"(d[O+39]), "+f"(d[O+40]), "+f"(d[O+41]), "+f"(d[O+42]), "+f"(d[O+43]), "+f"(d[O+44]), "+f"(d[O+45]), "+f"(d[O+46]), "+f"(d[O+47]), "+f"(d[O+48]), "+f"(d[O+49]), "+f"(d[O+50]), "+f"(d[O+51]), "+f"(d[O+52]), "+f"(d[O+53]), "+f"(d[O+54]), "+f"(d[O+55]), "+f"(d[O+56]), "+f"(d[O+57]), "+f"(d[O+58]), "+f"(d[O+59]), "+f"(d[O+60]), "+f"(d[O+61]), "+f"(d[O+62]), "+f"(d[O+63])
   : "r"(a0), "r"(a1), "r"(a2), "r"(a3), "l"(db), "n"(TB), "r"(sd));
}

#define NEARLY 0
#define XAHEAD 3
#define HEADN 6
#define WBATCH 1
#define WB 8
#define WSLEEP 20
#define XSPREAD 4
#define NOSEND 0
#define MSPLIT 2
#define PFALL 1
#define L2PF 0
#define STAG 0
#define EPF 2
#define XNB 2
#define FNB 0
#define GNB 0
#define TH 4
#define PF0 4
#define FSPLIT 1
#define MGLU 1
#define SPC 2
#define TL 14
#define GKB 4
#define T0A 7
#define T0B 11
#define TGATE 1
#define ZLATE 0
#define EARLYADD 0
#define OA 3
#define OB 11
#define EB 8
#define SPACE 100
#define WPF 1
#define WAFTER 7
#define WPACE 0
#define GATE_AT 4
#define TPACE 40
#define PFMODE 0
#define MAPMODE 1
template <int V> struct IC { static constexpr int value = V; };
struct Maps { CUtensorMap x, ft, g64, u64, e, wr, wi, xs, ts, t, g32, u32, d224, fg; };

constexpr int NCTA = 130;
constexpr int U = 16384;
constexpr int TB = 36864;
constexpr int OFF_RING = 8 * U, OFF_Z = 12 * U, OFF_XB = 12 * U, OFF_T = 13 * U, OFF_D = OFF_T;
constexpr int OFF_BAR = 14 * U, OFF_SP = OFF_BAR + 512, OFF_G = OFF_SP + 1024 + 128;
constexpr int SMEM_BYTES = OFF_G + 512;
constexpr int B_FX = 0, B_FA = 8, B_FT = 12, B_Z = 16, B_W = 24, B_HX = 25, B_TL = 26, B_HP = 27, B_WR = 31, B_E0 = 35;
constexpr int B_EA = 36, B_ET = 40, B_PZ = 44, B_RDY = 46, B_FE = 47, B_HF = 51;
constexpr int B_T = 53, B_XS = 54, B_G = 56, B_RD0 = 57, B_HS = 58, NBAR = 60;
__host__ __device__ constexpr int rslot(int n) { return n & 3; }
__host__ __device__ constexpr int rpar(int n) { return (n >> 2) & 1; }

__global__ void __cluster_dims__(2, 1, 1) __launch_bounds__(512, 1)
fused_kernel(Work* __restrict__ ws, const uint16_t* __restrict__ dtab, const __nv_bfloat16* __restrict__ w_r, const __nv_bfloat16* __restrict__ w_i,
             const __nv_bfloat16* __restrict__ gate_w, const __nv_bfloat16* __restrict__ x, __nv_bfloat16* __restrict__ out,
             const __grid_constant__ Maps maps) {
  extern __shared__ __align__(1024) uint8_t smem[];
  if (threadIdx.x < 32 && elect_one()) {
#pragma unroll
    for (int i = 0; i < PF0; i++) asm volatile("prefetch.tensormap [%0];" ::"l"((const char*)&maps + i * 128) : "memory");
  }
  const uint32_t sb = smem_u32(smem);
  const uint32_t bars = sb + OFF_BAR;
  const int tid = threadIdx.x, lane = tid & 31;
  const int warp = __shfl_sync(0xffffffffu, tid >> 5, 0);
  const bool helper = blockIdx.x >= 128;
  const int cl = (blockIdx.x >> 1) & 63, rank = blockIdx.x & 1;
  const int q4 = (cl & 1) | ((cl >> 2) & 2), rb = ((cl >> 1) & 3) | ((cl >> 4) << 2);
  const int j = 2 * q4 + rank;
  const int f_full = 448 * q4 + (rank ? 256 : 0);
  const int f_half = 448 * q4 + (rank ? 224 : 192);

  if (tid == 64) { PROF_EV(0); PROF_CK(40); }
  if (warp < 8) {
    if (!helper && tid < 32) {
      const int r = 16 * j + (tid & 15);
      asm volatile("prefetch.global.L2 [%0];" ::"l"(x + (size_t)(2 * rb + (r >> 6) + 32 * (r & 63)) * 512 + 64 * (tid >> 4)));
    }
    asm volatile("barrier.cluster.arrive.relaxed.aligned;" ::: "memory");
    asm volatile("setmaxnreg.inc.sync.aligned.u32 192;");
    if (!helper) {
      const int wg = warp >> 2, w = warp & 3, g = lane >> 2;
      const bool elect = (tid & 127) == 0;
      float cX[32], cA[64], cB[64], cC[64], ci[64], ct[64];
      const int zero = blockIdx.x >> 16;
      uint32_t h[56], yf[16];
      const uint32_t d0 = (sb & 0x3FFFF) >> 4;
      const uint32_t dK = d0 | (1u << 16), dN = d0 | (512u << 16);
      const uint32_t dX = dK + wg * 512;
      constexpr uint32_t RING = OFF_RING >> 4;
      auto waitA = [&](int n) { mbar_wait(bars + 8 * (B_FA + rslot(n)), rpar(n)); };
      auto freeA = [&](int n) { mbar_arrive_if(elect, bars + 8 * (B_EA + rslot(n))); };
      auto nop = [] {};

      asm volatile("bar.sync 0, 384;" ::: "memory");
#pragma unroll 1
      for (int i = 0; i < 4; i++) {
        const uint64_t dx = d128(dX + i * 2048), df = d128(dK + (OFF_XB >> 4) + (i & 1) * 1024);
        mbar_wait(bars + 8 * (B_FX + 2 * i), 0);
        wg_fence();
        mma_ss64<0, 0, 2>(cX, df, dx, i);
        mma_ss64<0, 0, 1>(cX, df + 2, dx + 2);
        wg_commit(); wg_wait<1>();
        mbar_arrive_if(elect && i, bars + 8 * (B_EA + rslot(i - 1)));
        mma_ss64<0, 0, 1>(cX, df + 4, dx + 4);
        mma_ss64<0, 0, 1>(cX, df + 6, dx + 6);
        if (i == 0 && tid == 0) PROF_EV(1);
        mbar_wait(bars + 8 * (B_FX + 2 * i + 1), 0);
        wg_fence();
#pragma unroll
        for (int k = 0; k < 4; k++) mma_ss64<0, 0, 1>(cX, df + (512 + k * 2), dx + (1024 + k * 2));
        wg_commit();
        waitA(i);
        wg_fence();
        const uint64_t da = d128(dX + i * 1024), db = d128(dN + RING + i * 1024);
        mma_ss128<0, 1, 2>(cA, da, db, i);
        wg_commit(); wg_wait<1>();
        mbar_arrive_if(elect, bars + 8 * (B_FE + i));
#pragma unroll
        for (int k = 1; k < 4; k++) mma_ss128<0, 1, 1>(cA, da + k * 2, db + k * 128);
        wg_commit();
      }
      fence_regs<0, 32>(cX);
#pragma unroll
      for (int e = 0; e < 16; e++) yf[e] = pack_pin(cX[2 * e], cX[2 * e + 1]);
      if (tid == 0) { PROF_EV(2); PROF_CK(42); }
      {
        waitA(4); mbar_wait(bars + 8 * B_E0, 0);
        const uint64_t de = d128(dN + (wg ? RING : OFF_XB >> 4));
        wg_fence();
        mma_rs128<0, 1, 0>(cB, yf[0], yf[1], yf[2], yf[3], de);
        wg_commit();
        wg_wait<1>();
        freeA(3);
#pragma unroll
        for (int k = 1; k < 4; k++) mma_rs128<0, 1, 1>(cB, yf[4 * k], yf[4 * k + 1], yf[4 * k + 2], yf[4 * k + 3], de + k * 128);
        wg_commit();
      }
      bool rel = false;
      auto acquire = [&](int n) {
        rel = elect;
        if (!mbar_try(bars + 8 * (B_FA + rslot(n)), rpar(n))) { wg_wait<0>(); freeA(n - 1); rel = false; waitA(n); }
      };
      auto freeP = [&](int n) { mbar_arrive_if(rel, bars + 8 * (B_EA + rslot(n - 1))); };
      auto ffn_step = [&](auto first, auto split, float (&acc)[64], int n, int kb, auto done, auto work) {
        constexpr int SPLIT = decltype(split)::value;
        acquire(n);
        wg_fence();
        const uint64_t dx = d128(dX + kb * 1024), db = d128(dN + RING + rslot(n) * 1024);
        mma_ss128<0, 1, decltype(first)::value>(acc, dx, db, kb);
#pragma unroll
        for (int k = 1; k < SPLIT; k++) mma_ss128<0, 1, 1>(acc, dx + k * 2, db + k * 128);
        wg_commit();
        work();
        wg_wait<1>();
        freeP(n);
        done();
        if (SPLIT < 4) {
          wg_fence();
#pragma unroll
          for (int k = SPLIT; k < 4; k++) mma_ss128<0, 1, 1>(acc, dx + k * 2, db + k * 128);
          wg_commit();
        }
      };
      {
        const int s0 = 2 * rb + wg, kr = 2 * ((s0 & 1) | ((s0 & 4) >> 1));
        const int m = lane >> 3, r = lane & 7;
        const uint32_t a0 = sb + OFF_XB + wg * 8192 + ((2 * (m >> 1) + (r >> 2)) * 2 + (w & 1)) * 256 + (m & 1) * 128 + (((2 * (r & 3) + ((w >> 1) ^ (r >> 2))) ^ (kr + (m & 1))) << 4);
        ffn_step(IC<1>(), IC<4>(), cA, 5, 4, [&] { fence_regs<0, 64>(cB); }, nop);
        asm volatile("bar.sync 5, 256;" ::: "memory");
        auto stage = [&](int i) {
          stsm4t(a0 + i * 2048, pack_bf16(cB[8 * i] - cB[34 + 8 * i], cB[8 * i + 1] - cB[35 + 8 * i]),
                 pack_bf16(cB[32 + 8 * i] + cB[8 * i + 2], cB[33 + 8 * i] + cB[8 * i + 3]),
                 pack_bf16(cB[8 * i + 4] - cB[38 + 8 * i], cB[8 * i + 5] - cB[39 + 8 * i]),
                 pack_bf16(cB[36 + 8 * i] + cB[8 * i + 6], cB[37 + 8 * i] + cB[8 * i + 7]));
          if (j == 0 && w == 0) {
            const uint32_t a1 = r ? sb + OFF_SP + 1024 : sb + OFF_SP + wg * 512 + (m & 1) * 256 + (m >> 1) * 128;
#pragma unroll
            for (int n = 2 * i; n < 2 * i + 2; n++)
              asm volatile("stmatrix.sync.aligned.m8n8.x4.shared.b16 [%0], {%1,%2,%3,%4};" ::"r"(a1 + ((n ^ (kr + (m >> 1)) ^ r) << 4)),
                           "r"(pack_bf16(cB[4 * n], cB[4 * n + 1])), "r"(pack_bf16(cB[4 * n + 2], cB[4 * n + 3])),
                           "r"(pack_bf16(cB[32 + 4 * n], cB[33 + 4 * n])), "r"(pack_bf16(cB[34 + 4 * n], cB[35 + 4 * n])) : "memory");
          }
        };
        auto publish = [&] {
          asm volatile("fence.proxy.async.shared::cta;" ::: "memory");
          __syncwarp();
          mbar_arrive_if(lane == 0, bars + 8 * (B_XS + wg));
          if (tid == 0) PROF_EV(3);
        };
        stage(0);
        ffn_step(IC<1>(), IC<FSPLIT>(), cA, 6, 5, nop, nop);
        stage(1);
        ffn_step(IC<1>(), IC<FSPLIT>(), cA, 7, 6, nop, nop);
        stage(2);
        ffn_step(IC<1>(), IC<2>(), cA, 8, 7, [&] { stage(3); }, nop);
        publish();
      }
      uint32_t gb0 = 0, gb1 = 0;
      uint32_t ob[2] = {0, 0};
      auto glu = [&](auto& acc, int half, int ho, int i0, int i1) {
#pragma unroll
        for (int i = i0; i < i1; i++)
          asm volatile("{\n.reg .b32 a, b;\ncvt.rn.relu.bf16x2.f32 a, %2, %1;\ncvt.rn.bf16x2.f32 b, %4, %3;\nmul.rn.bf16x2 a, a, b;\nmul.rn.bf16x2 %0, a, %5;\n}"
                       : "=r"(h[ho + i]) : "f"(acc[2 * i]), "f"(acc[2 * i + 1]), "f"(acc[half + 2 * i]), "f"(acc[half + 1 + 2 * i]), "r"(ob[i & 1]) : "memory");
      };
      ffn_step(IC<2>(), IC<1>(), cB, 9, zero, nop, nop);
#pragma unroll 1
      for (int kb = 1; kb < 8; kb++)
        ffn_step(IC<1>(), IC<FSPLIT>(), cB, 9 + kb, kb, nop, [&] {
          if (kb == GKB) {
            mbar_wait(bars + 8 * B_G, 0);
            asm volatile("ld.shared.u32 %0, [%2];\nld.shared.u32 %1, [%2+32];" : "=r"(gb0), "=r"(gb1) : "r"(sb + OFF_G + (wg * 64 + w * 16 + g) * 4) : "memory");
          } else if (kb == 5 + 2 * wg) {
            ob[0] = pack_bf16(1.0f - bf_hi(gb0), 1.0f - bf_hi(gb0)); ob[1] = pack_bf16(1.0f - bf_hi(gb1), 1.0f - bf_hi(gb1));
            glu(cA, 32, 0, 0, 16);
          }
        });
      const uint32_t tag = gb0 & 1;
      const float g0 = bf_hi(gb0), g1 = bf_hi(gb1);
      if (tid == 0) { PROF_EV(4); PROF_CK(43); }
      auto m_step = [&](auto first, int i) {
        acquire(17 + i);
        wg_fence();
        const uint64_t dx = d128(dX + i * 2048), dm = d64(dN + RING + rslot(17 + i) * 1024);
        mma_ss64<0, 1, decltype(first)::value>(ct, dx, dm);
#pragma unroll
        for (int k = 1; k < MSPLIT; k++) mma_ss64<0, 1, 1>(ct, dx + ((k >> 2) * 1024 + (k & 3) * 2), dm + k * 64);
        wg_commit();
        wg_wait<1>();
        freeP(17 + i);
        wg_fence();
#pragma unroll
        for (int k = MSPLIT; k < 8; k++) mma_ss64<0, 1, 1>(ct, dx + ((k >> 2) * 1024 + (k & 3) * 2), dm + k * 64);
        wg_commit();
      };
      m_step(IC<0>(), 0);
#pragma unroll 1
      for (int i = 1; i < 5; i++) {
        if (i == 1 + 2 * wg) glu(cB, 32, 16, 0, 16);
        if (i < 4) m_step(IC<1>(), i);
      }
      if (tid == 0) { PROF_EV(5); PROF_CK(44); }
      ffn_step(IC<0>(), IC<1>(), cC, 21, 0, nop, nop);
#pragma unroll 1
      for (int kb = 1; kb < 8; kb++)
        ffn_step(IC<1>(), IC<FSPLIT>(), cC, 21 + kb, kb, [&] { mbar_arrive_if(elect && !(kb & 1), bars + 8 * (B_ET + (kb >> 1) - 1)); }, [&] {
          if (kb == 1 + wg) glu(ct, 16, 48, 0, 8);
        });

      auto twait = [&](uint32_t bar, uint32_t par, int) { mbar_wait(bar, par); };
      auto tr = [] {};
      const int fo = warp * 128 + lane;
      auto fetch = [&](uint4 (&pv)[4], int z) {
        twait(bars + 8 * (z < 4 ? B_Z + 2 * z + wg : z < 6 ? B_HP + z - 4 : B_HP + 2 + wg), 0, 8 + z);
        const uint8_t* src = smem + (z < 4 ? OFF_Z - z * U : z == 4 ? OFF_T : (z - 5) * U) + fo * 16;
#pragma unroll
        for (int i = 0; i < 4; i++) pv[i] = *(const uint4*)(src + i * 512);
      };
      const uint32_t peerZ = mapa(sb + OFF_Z + fo * 16, rank ^ 1), peerB = mapa(bars + 8 * (B_Z + wg), rank ^ 1);
      auto tile_mma = [&](auto off, int t, int k0, int k1, bool fresh = false) {
        constexpr int O = decltype(off)::value;
        const uint64_t db = d128(dN + (t & 3) * (TB >> 4)), dw = db + rank * 256, dm = db + (rank ? 0 : 1536);
#pragma unroll
        for (int k = k0; k < k1; k++) {
          if (k == 0 && O == 0) mma_rs64<O, 1, 2>(ct, h[0], h[1], h[2], h[3], dw, zero);
          else if (k < 14) mma_rs64<O, 1, 1>(ct, h[4 * k], h[4 * k + 1], h[4 * k + 2], h[4 * k + 3], k < 12 ? dw + k * 128 : dm + (k - 12) * 128);
          else if (k == 14 && fresh) mma_rs64<O, 1, 0>(ct, yf[0], yf[1], yf[2], yf[3], db + k * 128);
          else if (k == 14) mma_rs64<O, 1, 2>(ct, yf[0], yf[1], yf[2], yf[3], db + k * 128, zero);
          else mma_rs64<O, 1, 1>(ct, yf[4 * k - 56], yf[4 * k - 55], yf[4 * k - 54], yf[4 * k - 53], db + k * 128);
        }
      };
      uint4 pv[4];
      const uint32_t sgn = rank ? 0x80008000u : 0u;
      auto even_end = [&](int t, int k0, bool fresh) {
        wg_fence();
        tile_mma(IC<32>(), t, 14, 18, fresh);
        wg_commit();
        tile_mma(IC<0>(), t, k0, 14);
        wg_commit();
        tr();
        wg_wait<1>();
        tr();
        fence_regs<32, 32>(ct);
#pragma unroll
        for (int i = 0; i < 4; i++)
          pv[i] = make_uint4(pack_pin(ct[32 + 8 * i], ct[33 + 8 * i]) ^ sgn, pack_pin(ct[34 + 8 * i], ct[35 + 8 * i]) ^ sgn,
                             pack_pin(ct[36 + 8 * i], ct[37 + 8 * i]) ^ sgn, pack_pin(ct[38 + 8 * i], ct[39 + 8 * i]) ^ sgn);
      };
      auto odd_head = [&](int t) {
        tr();
        twait(bars + 8 * (B_FT + (t & 3)), t >> 2, t);
        wg_fence();
        tile_mma(IC<32>(), t, 0, OA);
        wg_commit();
        tr();
        if (t < 4) twait(bars + 8 * (t == 1 ? B_RD0 : B_RDY), 0, 14 + t);
        wg_wait<1>();
        tr();
        mbar_arrive_if(elect && t < 6, bars + 8 * (B_ET + t - 1));
        fence_regs<0, 32>(ct);
        wg_fence();
#pragma unroll
        for (int i = 0; i < 4; i++) {
          asm volatile("st.async.weak.shared::cluster.mbarrier::complete_tx::bytes.v4.b32 [%0], {%2,%3,%4,%5}, [%1];" ::"r"(peerZ - (t >> 1) * U + i * 512),
                       "r"(peerB + 16 * (t >> 1)), "r"(add_bf2(pv[i].x, pack_bf16(ct[8 * i], ct[8 * i + 1]))), "r"(add_bf2(pv[i].y, pack_bf16(ct[8 * i + 2], ct[8 * i + 3]))),
                       "r"(add_bf2(pv[i].z, pack_bf16(ct[8 * i + 4], ct[8 * i + 5]))), "r"(add_bf2(pv[i].w, pack_bf16(ct[8 * i + 6], ct[8 * i + 7]))) : "memory");
          tile_mma(IC<32>(), t, OA + i, OA + i + 1);
        }
        wg_commit();
      };
      asm volatile("barrier.cluster.wait.aligned;" ::: "memory");
      twait(bars + 8 * B_FT, 0, 0);
      wg_fence();
      tile_mma(IC<0>(), 0, 0, T0A);
      wg_commit();
      waitA(29 + wg);
      wg_wait<1>();
      mbar_arrive_if(elect, bars + 8 * (B_ET + 3));
      glu(cC, 32, 32, 0, 16);
      if (tid == 0) PROF_EV(6);
      if (tid == 128) PROF_EV(27);
      mbar_wait(bars + 8 * (j == 0 ? B_T : B_TL), 0);
      if (tid == 0) { PROF_EV(7); PROF_CK(45); }
      wg_fence();
      {
        const uint64_t dt = d128(dN + (OFF_T >> 4) + wg * 512), de = d128(dK + RING + (1 + wg) * 1024);
        mma_ss64<0, 1, 0>(ci, de, dt);
        mma_ss64<32, 1, 0>(ci, de + 512, dt);
#pragma unroll
        for (int k = 1; k < 4; k++) {
          mma_ss64<0, 1, 1>(ci, de + k * 2, dt + k * 128);
          mma_ss64<32, 1, 1>(ci, de + (512 + k * 2), dt + k * 128);
        }
        wg_commit();
      }
      tile_mma(IC<0>(), 0, T0A, T0B);
      wg_commit();
      wg_wait<1>();
      if (elect) asm volatile("mbarrier.arrive.shared::cluster.b64 _, [%0];" ::"r"(mapa(bars + 8 * B_RDY, rank ^ 1)) : "memory");
      mbar_arrive_if(elect, bars + 8 * (B_PZ + 1));
      fence_regs<0, 64>(ci);
#pragma unroll
      for (int i = 0; i < 16; i++) {
        const float gg = ((i & 1) ? g1 : g0) * (2.0f / (2048.0f * 512.0f));
        if (i & 2) yf[i] = pack_pin((ci[2 * i] - ci[28 + 2 * i]) * gg, (ci[2 * i + 1] - ci[29 + 2 * i]) * gg);
        else yf[i] = pack_pin((ci[2 * i] + ci[36 + 2 * i]) * gg, (ci[2 * i + 1] + ci[37 + 2 * i]) * gg);
      }
      even_end(0, T0B, true);
      if (tid == 0) PROF_EV(8);
      if (tid == 128) PROF_EV(28);
#pragma unroll 1
      for (int t = 1; t < 7; t += 2) {
        odd_head(t);
        tr();
        wg_fence();
        tile_mma(IC<32>(), t, OA + 4, 14);
        wg_commit();
        tr();
        twait(bars + 8 * (B_FT + ((t + 1) & 3)), (t + 1) >> 2, t + 1);
        wg_fence();
        tile_mma(IC<0>(), t + 1, 0, TH);
        wg_commit();
        if (t > 1) twait(bars + 8 * (B_HF + wg), (t >> 2) & 1, 20);
        tr();
        wg_wait<1>();
        tr();
        mbar_arrive_if(elect && t < 5, bars + 8 * (B_ET + t));
        fence_regs<32, 32>(ct);
#pragma unroll
        for (int i = 0; i < 4; i++)
          asm volatile("st.shared.v4.u32 [%0], {%1,%2,%3,%4};" ::"r"(sb + (1 + 2 * wg) * TB + 28672 + w * 2048 + i * 512 + lane * 16),
                       "r"(pack_bf16(ct[32 + 8 * i], ct[33 + 8 * i])), "r"(pack_bf16(ct[34 + 8 * i], ct[35 + 8 * i])),
                       "r"(pack_bf16(ct[36 + 8 * i], ct[37 + 8 * i])), "r"(pack_bf16(ct[38 + 8 * i], ct[39 + 8 * i])) : "memory");
        __syncwarp();
        mbar_arrive_if(lane == 0, bars + 8 * (B_HS + wg));
        tr();
        wg_fence();
        tile_mma(IC<0>(), t + 1, TH, EB);
        wg_commit();
        tr();
        tr();
        even_end(t + 1, EB, false);
      }
      {
        uint4 p1[4], p2[4];
        auto acc4 = [&](uint4 (&d)[4], const uint4 (&a)[4]) {
#pragma unroll
          for (int i = 0; i < 4; i++) { d[i].x = add_bf2(d[i].x, a[i].x); d[i].y = add_bf2(d[i].y, a[i].y); d[i].z = add_bf2(d[i].z, a[i].z); d[i].w = add_bf2(d[i].w, a[i].w); }
        };
        auto add32 = [&](const uint4 (&a)[4]) {
#pragma unroll
          for (int i = 0; i < 4; i++) {
            const uint32_t u[4] = {a[i].x, a[i].y, a[i].z, a[i].w};
#pragma unroll
            for (int e = 0; e < 4; e++) { ct[32 + 8 * i + 2 * e] += bf_lo(u[e]); ct[33 + 8 * i + 2 * e] += bf_hi(u[e]); }
          }
        };
        odd_head(7);
        fetch(pv, 4);
        fetch(p1, 5);
        wg_fence();
        tile_mma(IC<32>(), 7, OA + 4, OB);
        wg_commit();
        uint32_t bad = 0;
#pragma unroll
        for (int i = 0; i < 4; i++) { bad |= (pv[i].x ^ tag) | (p1[i].x ^ tag); pv[i].x &= ~1u; p1[i].x &= ~1u; }
        acc4(pv, p1);
        fetch(p1, 3);
        wg_fence();
        tile_mma(IC<32>(), 7, OB, 14);
        wg_commit();
        if (tid == 0) { PROF_EV(9); PROF_CK(46); }
        if (tid == 128) PROF_EV(29);
        fetch(p2, 6);
        if (tid == 0) PROF_EV(24);
        wg_wait<0>();
        fence_regs<32, 32>(ct);
#pragma unroll
        for (int i = 0; i < 4; i++) bad |= p2[i].x ^ tag;
        if (__any_sync(0xffffffffu, bad & 1)) {
          const uint4* src = ws->part + (size_t)(rb * 8 + j) * 3 * 1024 + fo;
          uint4 p0[4];
          int n = 0;
          do {
            bad = 0;
#pragma unroll
            for (int i = 0; i < 4; i++) {
              pv[i] = ld_x4(src + i * 32); p0[i] = ld_x4(src + 1024 + i * 32); p2[i] = ld_x4(src + 2048 + i * 32);
              bad |= (pv[i].x ^ tag) | (p0[i].x ^ tag) | (p2[i].x ^ tag);
            }
            if (++n > (1 << 21)) __trap();
          } while (__any_sync(0xffffffffu, bad & 1));
#pragma unroll
          for (int i = 0; i < 4; i++) { pv[i].x &= ~1u; p0[i].x &= ~1u; }
          acc4(pv, p0);
        }
#pragma unroll
        for (int i = 0; i < 4; i++) p2[i].x &= ~1u;
        acc4(p1, p2);
        add32(pv); add32(p1);
#pragma unroll
        for (int i = 0; i < 4; i++)
          pv[i] = make_uint4(pack_bf16(ct[32 + 8 * i], ct[33 + 8 * i]), pack_bf16(ct[34 + 8 * i], ct[35 + 8 * i]), pack_bf16(ct[36 + 8 * i], ct[37 + 8 * i]), pack_bf16(ct[38 + 8 * i], ct[39 + 8 * i]));
        if (tid == 0) PROF_EV(14);
        const uint32_t stg = sb + OFF_T + warp * 2048;
        const int mr = (lane & 7) + ((lane >> 3) & 1) * 8, mc = lane >> 4;
#pragma unroll
        for (int i = 0; i < 4; i++)
          asm volatile("stmatrix.sync.aligned.m8n8.x4.shared.b16 [%0], {%1,%2,%3,%4};" ::"r"(stg + mr * 128 + (((2 * i + mc) ^ (mr & 7)) << 4)), "r"(pv[i].x),
                       "r"(pv[i].y), "r"(pv[i].z), "r"(pv[i].w) : "memory");
        __syncwarp();
#pragma unroll
        for (int i = 0; i < 4; i++) {
          const int r = 4 * i + (lane >> 3), c = lane & 7;
          const uint4 v = *(const uint4*)(smem + OFF_T + warp * 2048 + r * 128 + ((c ^ (r & 7)) << 4));
          *(uint4*)(out + (size_t)(2 * rb + wg + 32 * (16 * w + r)) * 512 + 64 * (q4 + 4 * rank) + 8 * c) = v;
        }
      }
      if (tid == 0) { PROF_EV(15); PROF_CK(41); }
      if (tid == 128) PROF_EV(30);
    }
  } else if (warp < 12) {
    asm volatile("setmaxnreg.dec.sync.aligned.u32 104;");
    asm volatile("barrier.cluster.arrive.relaxed.aligned;" ::: "memory");
    const int t = tid - 256, w = warp - 8;
    const uint32_t ep = ld_x1(&ws->epoch[blockIdx.x * 8]);
    const uint32_t tag = (ep + 1) & 1;
    auto w_issue = [&](const CUtensorMap* m) {

      if (elect_one()) { mbar_expect_tx(bars + 8 * (B_WR + w), 3072); tma4d(sb + OFF_T + w * 3072, m, bars + 8 * (B_WR + w), 32 * j, 0, 4 * (rb & 1) + w, rb >> 1); }

          __syncwarp();
    };
    auto gate_rows = [&] {
      const int r = 16 * j + 4 * w + (lane >> 3);
      const uint4* pg = (const uint4*)gate_w + (lane & 7);
      {
        float a = 0.f;
        asm volatile("bar.sync 4, 256;" ::: "memory");
#pragma unroll 1
        for (int hf = 0; hf < 2; hf++) {
          uint4 v[4], u[4];
#pragma unroll
          for (int kb = 0; kb < 4; kb++) v[kb] = __ldg(pg + (4 * hf + kb) * 8);
          mbar_wait(bars + 8 * (B_FE + 1 + 2 * hf), 0);
          if (hf) w_issue(&maps.wr);
#pragma unroll
          for (int kb = 0; kb < 4; kb++) u[kb] = *(const uint4*)(smem + (4 * hf + kb) * U + r * 128 + (((lane ^ r) & 7) << 4));
#pragma unroll
          for (int kb = 0; kb < 4; kb++) {
            const uint32_t uu[4] = {u[kb].x, u[kb].y, u[kb].z, u[kb].w}, vv[4] = {v[kb].x, v[kb].y, v[kb].z, v[kb].w};
#pragma unroll
            for (int e = 0; e < 4; e++) {
              uint32_t pr;
              asm("mul.rn.bf16x2 %0, %1, %2;" : "=r"(pr) : "r"(uu[e]), "r"(vv[e]));
              a += bf_lo(pr) + bf_hi(pr);
            }
          }
        }
#pragma unroll
        for (int o = 4; o; o >>= 1) a += __shfl_xor_sync(0xffffffffu, a, o);
        if ((lane & 7) == 0)
          asm volatile("st.relaxed.gpu.global.u32 [%0], %1;" ::"l"(ws->gate + rb * 128 + r),
                       "r"(pack_bf16(0.f, __fdividef(1.0f, 1.0f + __expf(-bf_lo(pack_bf16(a, 0.f))))) | tag) : "memory");
        if (t == 0) PROF_EV(18);
      }
    };
    {
      const int g = lane >> 2, q = lane & 3;
      uint32_t wf[32];
      if (!helper) {
        gate_rows();
        const uint32_t wa = sb + OFF_T + w * (3072 + 2) + (rb & 1) * 8 + q * 96 + g * 4, wb[2] = {wa + (rb & 1) * 32, wa + 32 - (rb & 1) * 32};
#pragma unroll 1
        for (int ri = 0; ri < 2; ri++) {
          mbar_wait(bars + 8 * (B_WR + w), ri);
#pragma unroll
          for (int n2 = 0; n2 < 32 / WB; n2++) {
            uint32_t v[WB];
#pragma unroll
            for (int i = 0; i < WB; i++) {
              const int e = n2 * WB + i;
              asm volatile("ld.shared.u16 %0, [%1];" : "=r"(v[i]) : "r"(wb[e & 1] + ((e >> 1) & 7) * 384 + (e >> 4) * 2) : "memory");
            }
#pragma unroll
            for (int i = 0; i < WB; i++) wf[n2 * WB + i] = __byte_perm(wf[n2 * WB + i], v[i], 0x5432);
            if (WSLEEP) { asm volatile("nanosleep.u32 %0;" ::"r"(WSLEEP + (v[WB - 1] >> 16)) : "memory"); }
          }
          __syncwarp();
          if (ri == 0) w_issue(&maps.wi);
        }
        asm volatile("bar.sync 1, 128;" ::: "memory");
        if (t == 0) PROF_EV(11);
      } else {
        asm volatile("bar.sync 4, 256;" ::: "memory");
        hint_wait(&ws->cntW[0], (ep + 1) * 128u);
        const uint32_t t0 = (uint32_t)clock();
#pragma unroll 1
        for (;;) {
          uint32_t bad = 0;
#pragma unroll
          for (int i = 0; i < 32; i++) {
            const float2 v = ld_x2((const float2*)ws->Wh + (i >> 4) * 2048 + 16 * w + g + 8 * (i & 1) + 64 * q + ((i >> 1) & 7) * 256);
            wf[i] = __float_as_uint(v.x); bad |= __float_as_uint(v.y) ^ tag;
          }
          if (!__any_sync(0xffffffffu, bad & 1)) break;
          spin_guard(t0);
        }
        if (t == 0) PROF_EV(11);
      }
      if (w == 0 && elect_one()) { mbar_expect_tx(bars + 8 * B_W, 8192); bulk_load(sb + OFF_D, dtab, 8192, bars + 8 * B_W); }
      asm volatile("barrier.cluster.wait.aligned;" ::: "memory");
      mbar_wait(bars + 8 * B_W, 0);
      mbar_wait(bars + 8 * B_HX, 0);
      if (t == 0) PROF_EV(12);
      const uint32_t dd = (sb & 0x3FFFF) >> 4;
      const uint64_t dF = d128((dd + (OFF_D >> 4)) | (512u << 16)), dI = d128((dd + (OFF_D >> 4)) | (1u << 16)), dA = d128((dd + (OFF_XB >> 4)) | (512u << 16));
      float az[32];
      const int zero = blockIdx.x >> 16;
      uint32_t pf[32];
#pragma unroll
      for (int mt = 0; mt < 2; mt++) {
        wg_fence();
        if (mt == 0) mma_ss64<0, 3, 0>(az, dA, dF);
        else mma_ss64<0, 3, 2>(az, dA + 512, dF, zero);
#pragma unroll
        for (int k = 1; k < 4; k++) mma_ss64<0, 3, 1>(az, dA + (mt * 512 + k * 128), dF + k * 128);
        wg_commit();
        wg_wait<0>();
        fence_regs<0, 32>(az);
#pragma unroll
        for (int i = 0; i < 16; i++) {
          const float wr = bf_lo(wf[16 * mt + i]), wi = bf_hi(wf[16 * mt + i]);
          pf[16 * mt + i] = pack_pin(fmaf(az[2 * i], wr, -az[2 * i + 1] * wi), fmaf(az[2 * i], wi, az[2 * i + 1] * wr));
        }
      }
      if (t == 0) PROF_EV(16);
      {
        const int m = lane >> 3, r = lane & 7;
        const int sl = 2 * (m >> 1) + ((r >> 1) & 1) + 4 * (r >> 2);
        const uint32_t a0 = sb + OFF_XB + w * 4096 + sl * 64 + (((((m ^ rb) & 1) * 2 + (r & 1)) ^ (sl >> 1)) << 4);
        uint32_t pk[16];
#pragma unroll
        for (int mt = 0; mt < 3; mt++) {
          if (mt < 2) {
            wg_fence();
            mma_rs64<0, 0, 2>(az, pf[16 * mt], pf[16 * mt + 1], pf[16 * mt + 2], pf[16 * mt + 3], dI, mt ? (int)helper : zero);
#pragma unroll
            for (int k = 1; k < 4; k++) mma_rs64<0, 0, 1>(az, pf[16 * mt + 4 * k], pf[16 * mt + 4 * k + 1], pf[16 * mt + 4 * k + 2], pf[16 * mt + 4 * k + 3], dI + k * 2);
            wg_commit();
          }
          if (mt > 0 && !helper) {
#pragma unroll
            for (int i = 0; i < 4; i++) stsm4t(a0 + (mt - 1) * 2048 + i * 512, pk[4 * i], pk[4 * i + 1], pk[4 * i + 2], pk[4 * i + 3]);
          }
          if (mt < 2) {
            wg_wait<0>();
            fence_regs<0, 32>(az);
#pragma unroll
            for (int i = 0; i < 16; i++) pk[i] = pack_pin(az[2 * i], az[2 * i + 1]);
          }
        }
      }
      if (helper) {
#pragma unroll
        for (int i = 0; i < 16; i++) {
          const int n = i >> 1, s0 = 8 * (n >> 1) + 2 * (n & 1) + (q & 1) + 4 * (q >> 1);
          if ((n & 1) == (int)(blockIdx.x & 1)) st_u2(ws->Ts + s0 * 64 + 16 * w + g + 8 * (i & 1), pack_bf16(az[2 * i], az[2 * i + 1]), tag);
        }
        __syncwarp();
        hint_add_if(lane == 0, &ws->cntH[0]);
        if (t == 0) { ws->epoch[blockIdx.x * 8] = ep + 1; PROF_EV(13); }
      } else {
        asm volatile("fence.proxy.async.shared::cta;" ::: "memory");
        __syncwarp();
        if (elect_one()) {
          if (t == 0) PROF_EV(17);
          if (SPACE) __nanosleep(SPACE * w);
          asm volatile("cp.async.bulk.tensor.4d.global.shared::cta.bulk_group [%0, {%2, %3, %4, %5}], [%1];" ::"l"(&maps.ts), "r"(sb + OFF_XB + w * 4096),
                       "r"(32 * rank), "r"(0), "r"(2 * q4), "r"(4 * rb + w) : "memory");
          bulk_done_signal(&ws->cntT[32 * q4]);
          asm volatile("mbarrier.arrive.shared::cluster.b64 _, [%0];" ::"r"(mapa(bars + 8 * B_RD0, rank ^ 1)) : "memory");
          if (t == 96) PROF_EV(13);
        }
        __syncwarp();
        if (j == 0) {
          hint_wait(&ws->cntH[0], (ep + 1) * 8u);
          const uint32_t t0 = (uint32_t)clock();
          float2 v;
          do { v = ld_x2((const float2*)ws->Ts + 2 * rb * 64 + t); spin_guard(t0); } while (__any_sync(0xffffffffu, (__float_as_uint(v.y) ^ tag) & 1));
          mbar_wait(bars + 8 * B_TL, 0);
          const uint32_t u = __float_as_uint(v.x);
          *(uint16_t*)(smem + OFF_T + t * 128 + ((t & 7) << 4)) = (uint16_t)u;
          *(uint16_t*)(smem + OFF_T + t * 128 + (((t & 7) ^ 1) << 4)) = (uint16_t)(u >> 16);
          asm volatile("fence.proxy.async.shared::cta;" ::: "memory");
          __syncwarp();
          mbar_arrive_if(lane == 0, bars + 8 * B_T);
        }
        const int hw = w >> 1;
#pragma unroll 1
        for (int z = 0; z < 3; z++) {
          const int owner = rb * 8 + 2 * ((q4 + z + 1) & 3) + rank;
          uint4* dst = ws->part + (size_t)(owner * 3 + z) * 1024 + w * 256 + lane;
          const uint8_t* pa = smem + (1 + 2 * hw) * TB + 28672 + (w & 1) * 4096 + lane * 16;
          const uint8_t* pb = smem + OFF_Z - z * U + w * 4096 + lane * 16;
          uint4 a[8], b[8];
          mbar_wait(bars + 8 * (B_Z + 2 * z + hw), 0);
#pragma unroll
          for (int i = 0; i < 8; i++) b[i] = *(const uint4*)(pb + i * 512);
          mbar_wait(bars + 8 * (B_HS + hw), z & 1);
#pragma unroll
          for (int i = 0; i < 8; i++) a[i] = *(const uint4*)(pa + i * 512);
#pragma unroll
          for (int i = 0; i < 8; i++)
            asm volatile("st.relaxed.gpu.global.v4.u32 [%0], {%1,%2,%3,%4};" ::"l"(dst + i * 32), "r"((add_bf2(a[i].x, b[i].x) & ~1u) | tag),
                         "r"(add_bf2(a[i].y, b[i].y)), "r"(add_bf2(a[i].z, b[i].z)), "r"(add_bf2(a[i].w, b[i].w)) : "memory");
          hint_add_if(lane == 0, &ws->cntP[32 * owner + 8 * (z + (z == 2 ? hw : 0))]);
          __syncwarp();
          mbar_arrive_if(lane == 0, bars + 8 * (B_HF + hw));
        }
      }
    }
  } else {
    asm volatile("setmaxnreg.dec.sync.aligned.u32 24;");
    auto xf_load = [&](int q) {
      const uint32_t fb = bars + 8 * (B_FX + q);
      mbar_expect_tx(fb, U + 8192);
      tma3d(sb + q * U, &maps.x, fb, 64 * q, 0, 2 * rb);
      if (q >= 4) mbar_wait(bars + 8 * (B_FE + ((q - 4) >> 1)), 0);
      tma2d(sb + OFF_XB + (q & 3) * 8192, &maps.ft, fb, 64 * q, 64 * j);
    };
    if (elect_one()) {
      if (warp == 14) {
#pragma unroll
        for (int i = 0; i < B_FT; i++) mbar_init(bars + 8 * i, 1);
        asm volatile("fence.mbarrier_init.release.cluster;" ::: "memory");
        if (!helper) {
#pragma unroll 1
          for (int n = 0; n < 2; n++) {
            const uint32_t fb = bars + 8 * (B_FA + n);
            xf_load(2 * n); xf_load(2 * n + 1);
            mbar_expect_tx(fb, U);
            tma2d(sb + OFF_RING + n * U, &maps.g64, fb, f_full, 64 * n);
            tma2d(sb + OFF_RING + n * U + 8192, &maps.u64, fb, f_full, 64 * n);
          }
        }
      } else if (warp == 15) {
#pragma unroll
        for (int i = B_FT; i < NBAR; i++) mbar_init(bars + 8 * i, i < B_EA ? 1 : i < B_T ? 2 : 4);
#pragma unroll
        for (int i = 0; i < 8; i++) mbar_expect_tx(bars + 8 * (B_Z + i), U / 2);
        asm volatile("fence.mbarrier_init.release.cluster;" ::: "memory");
        asm volatile("fence.proxy.async.shared::cta;" ::: "memory");
      }
    }
    __syncwarp();
    asm volatile("bar.arrive 0, 384;" ::: "memory");
    asm volatile("bar.arrive 4, 256;" ::: "memory");
    __syncwarp();
    asm volatile("barrier.cluster.arrive.relaxed.aligned;" ::: "memory");
    asm volatile("bar.sync 3, 128;" ::: "memory");
    if (warp == 15 && !helper) {
        mbar_wait(bars + 8 * B_FE, 0);
        const uint32_t tag = (ld_x1(&ws->epoch[blockIdx.x * 8]) + 1) & 1;
        const int c = lane >> 4, jj = 16 * blockIdx.x + (lane & 15), jm = (2048 - jj) & 2047;
        const unsigned short* pr = (const unsigned short*)w_r + 256 * c;
        const unsigned short* pi = (const unsigned short*)w_i + 256 * c;
        const float wr = 0.25f * (bf_lo(__ldg(pr + jj * 257)) + bf_lo(__ldg(pr + jm * 257)));
        const float wi = 0.25f * (bf_lo(__ldg(pi + jj * 257)) - bf_lo(__ldg(pi + jm * 257)));
        st_u2(ws->Wh + c * 2048 + jj, c ? pack_bf16(-wi, wr) : pack_bf16(wr, wi), tag);
        __syncwarp();
        hint_add_if(lane == 0, &ws->cntW[0]);
        mbar_wait(bars + 8 * B_XS, 0);
        const uint32_t t0 = (uint32_t)clock();
        uint4 v;
        do { v = ld_x4(ws->gate + rb * 128 + 4 * lane); spin_guard(t0); } while (__any_sync(0xffffffffu, ((v.x ^ tag) | (v.y ^ tag) | (v.z ^ tag) | (v.w ^ tag)) & 1));
        *(uint4*)(smem + OFF_G + lane * 16) = v;
        __syncwarp();
        mbar_arrive_if(lane < 4, bars + 8 * B_G);
      }
    auto part_load = [&](int i, unsigned ep1) {
      const uint32_t bytes = i < 2 ? U : U / 2;
      mbar_wait(bars + 8 * (B_PZ + (i == 0)), 0);
      mbar_expect_tx(bars + 8 * (B_HP + i), bytes);
      flag_wait(&ws->cntP[32 * (rb * 8 + j) + 8 * i], ep1 * (i < 2 ? 4u : 2u));
      bulk_load(sb + (i == 0 ? OFF_T : i == 1 ? 0 : i * (U / 2)), ws->part + (size_t)(rb * 8 + j) * 3072 + (i < 2 ? i * 1024 : 1024 + i * 512), bytes, bars + 8 * (B_HP + i));
      if (i == 2) PROF_EV(26);
    };
    if ((!helper || warp == 15) && elect_one()) {
      if (warp < 14) {
        const int p = warp - 12;
#pragma unroll 1
        for (int i = 4 + p; i < 14; i += 2) asm volatile("prefetch.tensormap [%0];" ::"l"((const char*)&maps + i * 128) : "memory");
#pragma unroll 1
        for (int n = 2; n < 31; n++) {
          const bool table = n == 4 || n >= 29;
          const bool half = n >= 17 && n < 21;
          const int q = n < 4 ? n : n < 17 ? n - 1 : n - 5;
          const CUtensorMap* m = table ? &maps.e : half ? &maps.g32 + p : &maps.g64 + p;
          const int c0 = table ? 0 : half ? f_half : f_full + 64 * (q >> 3);
          const int c1 = table ? (2 * rb + ((n & 1) ^ 1)) * 128 + 64 * p : half ? 128 * (n - 17) : 64 * (q & 7);
          const uint32_t fb = bars + 8 * (B_FA + (n & 3)), dst = sb + OFF_RING + (n & 3) * U + p * 8192;
          if (n < 4) mbar_wait(bars + 8 * (B_FE + n - 2), 0);
          else mbar_wait(bars + 8 * (B_EA + (n & 3)), ((n >> 2) & 1) ^ 1);
          tma2d(dst, m, fb, c0, c1);
          if (p == 0) mbar_expect_tx(fb, U);
        }
        part_load(2 + p, ld_x1(&ws->epoch[blockIdx.x * 8]) + 1);
      } else if (warp == 15) {
        const unsigned ep1 = ld_x1(&ws->epoch[blockIdx.x * 8]) + 1;
        flag_wait(&ws->cntX[helper ? 0 : 32 * j], ep1 * 16u);
        PROF_EV(22);
        mbar_expect_tx(bars + 8 * B_HX, U);
        bulk_load(sb + OFF_XB, ws->X + (size_t)(helper ? 128 : 16 * j + rb) * 8192, U, bars + 8 * B_HX);
        if (!helper) {
          flag_wait(&ws->cntT[32 * q4], ep1 * 128u);
          PROF_EV(23);
          mbar_expect_tx(bars + 8 * B_TL, U);
          tma3d(sb + OFF_T, &maps.t, bars + 8 * B_TL, 64 * j, 0, 2 * rb);
          part_load(0, ep1); part_load(1, ep1);
          mbar_wait(bars + 8 * (B_HP + 2), 0); mbar_wait(bars + 8 * (B_HP + 3), 0);
          ws->epoch[blockIdx.x * 8] = ep1;
        }
      } else {
#pragma unroll 1
        for (int q = 4; q < 8; q++) xf_load(q);
        mbar_wait(bars + 8 * (B_FE + 2), 0);
        mbar_expect_tx(bars + 8 * B_E0, U);
        tma2d(sb + OFF_XB, &maps.e, bars + 8 * B_E0, 0, 2 * rb * 128);
        tma2d(sb + OFF_XB + 8192, &maps.e, bars + 8 * B_E0, 0, 2 * rb * 128 + 64);
#pragma unroll 1
        for (int h2 = 0; h2 < 2; h2++) {
          const int s0 = 2 * rb + h2, sg = (s0 & ~6) | ((s0 & 2) << 1) | ((s0 & 4) >> 1);
          mbar_wait(bars + 8 * (B_XS + h2), 0);
#pragma unroll 1
          for (int c = 0; c < 2; c++) {
            asm volatile("cp.async.bulk.tensor.4d.global.shared::cta.bulk_group [%0, {%2, %3, %4, %5}], [%1];" ::"l"(&maps.xs),
                         "r"(sb + OFF_XB + h2 * 8192 + c * 4096), "r"(0), "r"(sg), "r"(0), "r"(16 * j + 8 * c) : "memory");
            if (j == 0)
              asm volatile("cp.async.bulk.global.shared::cta.bulk_group [%0], [%1], 256;" ::"l"(ws->X + 128 * 8192 + c * 4096 + sg * 128),
                           "r"(sb + OFF_SP + h2 * 512 + c * 256) : "memory");
            if (SPACE && h2 + c < 2) __nanosleep(SPACE);
          }
        }
        bulk_done_signal(&ws->cntX[32 * j]);
        PROF_EV(20);
#pragma unroll 1
        for (int t = 0; t < 8; t++) {
          const int col = 64 * (((q4 + 1 + (t >> 1)) & 3) + 4 * ((t & 1) ? rank : 1 - rank));
          const uint32_t fb = bars + 8 * (B_FT + (t & 3)), dst = sb + (t & 3) * TB;
          mbar_wait(bars + 8 * (B_ET + (t < 3 ? t + 1 : t & 3)), t >> 2);
          mbar_expect_tx(fb, (t & 1) ? 28672 : TB);
          tma2d(dst, &maps.d224, fb, col, 224 * j);
          if (!(t & 1)) tma3d(dst + 28672, &maps.fg, fb, col ^ 256, 16 * rank, 4 * q4);
        }
      }
    }
  }
}

typedef CUresult (*EncodeFn)(CUtensorMap*, CUtensorMapDataType, cuuint32_t, void*, const cuuint64_t*, const cuuint64_t*, const cuuint32_t*,
                             const cuuint32_t*, CUtensorMapInterleave, CUtensorMapSwizzle, CUtensorMapL2promotion, CUtensorMapFloatOOBfill);

static void encode(EncodeFn f, CUtensorMap* m, const void* base, int rank, const cuuint64_t* dims, const cuuint64_t* strides, const cuuint32_t* box,
                   CUtensorMapSwizzle sw) {
  cuuint32_t es[5] = {1, 1, 1, 1, 1};
  f(m, CU_TENSOR_MAP_DATA_TYPE_BFLOAT16, rank, (void*)base, dims, strides, box, es, CU_TENSOR_MAP_INTERLEAVE_NONE, sw,
    CU_TENSOR_MAP_L2_PROMOTION_L2_128B, CU_TENSOR_MAP_FLOAT_OOB_FILL_NONE);
}

extern "C" void kernel_launch(void* const* d_in, const int* in_sizes, int n_in, void* d_out, int out_size) {
  (void)in_sizes; (void)n_in; (void)out_size;
  const __nv_bfloat16* x = (const __nv_bfloat16*)d_in[0];
  const __nv_bfloat16* w_r = (const __nv_bfloat16*)d_in[1];
  const __nv_bfloat16* w_i = (const __nv_bfloat16*)d_in[2];
  const __nv_bfloat16* Wg = (const __nv_bfloat16*)d_in[4];
  const __nv_bfloat16* Wu = (const __nv_bfloat16*)d_in[5];
  const __nv_bfloat16* Wd = (const __nv_bfloat16*)d_in[6];
  const __nv_bfloat16* gw = (const __nv_bfloat16*)d_in[7];

  void* fp = nullptr; cudaDriverEntryPointQueryResult qr;
  cudaGetDriverEntryPoint("cuTensorMapEncodeTiled", &fp, cudaEnableDefault, &qr);
  EncodeFn enc = (EncodeFn)fp;
  void *pFT, *pET, *pDT, *pW;
  cudaGetSymbolAddress(&pDT, g_DT); cudaGetSymbolAddress(&pW, g_work);
  void *pX = ((Work*)pW)->X, *pT = ((Work*)pW)->T;
  cudaGetSymbolAddress(&pFT, g_FT); cudaGetSymbolAddress(&pET, g_ET);

  Maps mp;
  const CUtensorMapSwizzle S128 = CU_TENSOR_MAP_SWIZZLE_128B, S64 = CU_TENSOR_MAP_SWIZZLE_64B;
  { cuuint64_t d[3] = {512, 64, 32}, s[2] = {32768, 1024}; cuuint32_t b[3] = {64, 64, 2}; encode(enc, &mp.x, x, 3, d, s, b, S128); }
  { cuuint64_t d[2] = {512, 512}, s[1] = {1024}; cuuint32_t b[2] = {64, 64}; encode(enc, &mp.ft, pFT, 2, d, s, b, S128); }
  { cuuint64_t d[4] = {128, 32, 2, 129}, s[3] = {256, 8192, 16384}; cuuint32_t b[4] = {128, 1, 2, 8}; encode(enc, &mp.xs, pX, 4, d, s, b, CU_TENSOR_MAP_SWIZZLE_NONE); }
  { cuuint64_t d[4] = {64, 32, 8, 64}, s[3] = {65536, 128, 1024}; cuuint32_t b[4] = {32, 32, 2, 1}; encode(enc, &mp.ts, pT, 4, d, s, b, S64); }
  { cuuint64_t d[3] = {512, 32, 16}, s[2] = {1024, 32768}; cuuint32_t b[3] = {64, 16, 4}; encode(enc, &mp.fg, pFT, 3, d, s, b, S128); }
  { cuuint64_t d[3] = {512, 64, 32}, s[2] = {1024, 65536}; cuuint32_t b[3] = {64, 64, 2}; encode(enc, &mp.t, pT, 3, d, s, b, S128); }
  { cuuint64_t d[2] = {64, 4096}, s[1] = {128}; cuuint32_t b[2] = {64, 64}; encode(enc, &mp.e, pET, 2, d, s, b, S128); }
  { cuuint64_t d[2] = {1792, 512}, s[1] = {3584}; cuuint32_t b[2] = {64, 64}, b2[2] = {32, 128};
    encode(enc, &mp.g64, Wg, 2, d, s, b, S128); encode(enc, &mp.u64, Wu, 2, d, s, b, S128);
    encode(enc, &mp.g32, Wg, 2, d, s, b2, S64); encode(enc, &mp.u32, Wu, 2, d, s, b2, S64); }
  { cuuint64_t d[2] = {512, 1792}, s[1] = {1024}; cuuint32_t b[2] = {64, 224}; encode(enc, &mp.d224, Wd, 2, d, s, b, S128); }
  { cuuint64_t d[4] = {264, 32, 8, 8}, s[3] = {32896, 512, 4112}; cuuint32_t b[4] = {48, 32, 1, 1};
    encode(enc, &mp.wr, w_r, 4, d, s, b, CU_TENSOR_MAP_SWIZZLE_NONE); encode(enc, &mp.wi, w_i, 4, d, s, b, CU_TENSOR_MAP_SWIZZLE_NONE); }

  cudaFuncSetAttribute(fused_kernel, cudaFuncAttributeMaxDynamicSharedMemorySize, SMEM_BYTES);
  fused_kernel<<<NCTA, 512, SMEM_BYTES>>>((Work*)pW, (const uint16_t*)pDT, w_r, w_i, gw, x, (__nv_bfloat16*)d_out, mp);
}
```

```cpp
#include <cuda_runtime.h>
#include <cuda_bf16.h>
#include <cuda.h>
#include <stdint.h>

namespace tbl {
constexpr double PI = 3.14159265358979323846264338327950288;
constexpr double sin_s(double x) { double t = x, s = x; for (int n = 1; n < 12; n++) { t *= -x * x / ((2 * n) * (2 * n + 1)); s += t; } return s; }
constexpr double cos_s(double x) { double t = 1, s = 1; for (int n = 1; n < 12; n++) { t *= -x * x / ((2 * n - 1) * (2 * n)); s += t; } return s; }
constexpr double cos2048(int m) {
  m &= 2047; if (m > 1024) m = 2048 - m;
  bool neg = false; if (m > 512) { m = 1024 - m; neg = true; }
  double v = (m <= 256) ? cos_s(2 * PI * m / 2048) : sin_s(2 * PI * (512 - m) / 2048);
  return neg ? -v : v;
}
constexpr uint16_t to_bf16(double v) {
  if (v == 0) return 0;
  uint16_t s = 0; if (v < 0) { s = 0x8000; v = -v; }
  int e = 0; while (v >= 2) { v /= 2; e++; } while (v < 1) { v *= 2; e--; }
  double m = (v - 1) * 128; int mi = (int)m; double fr = m - mi;
  if (fr > 0.5 || (fr == 0.5 && (mi & 1))) mi++;
  if (mi == 128) { mi = 0; e++; }
  return (uint16_t)(s | ((e + 127) << 7) | mi);
}
struct CosT { uint16_t v[2048]; constexpr CosT() : v() { for (int i = 0; i < 2048; i++) v[i] = to_bf16(cos2048(i)); } };
struct alignas(1024) FT {
  uint16_t v[512 * 512];
  constexpr FT() : v() {
    CosT c;
    for (int r = 0; r < 512; r++) {
      int k = (r >> 5) * 16 + 2 * (r & 7) + ((r >> 4) & 1), e = (r >> 3) & 1;
      int mul = 4 * k, add = e ? 512 : 0;
      if (k == 0 && e == 1) { mul = 1024; add = 0; }
      for (int d = 0; d < 512; d++) v[r * 512 + d] = c.v[(d * mul + add) & 2047];
    }
  }
};
struct alignas(1024) ET {
  uint16_t v[2048 * 128];
  constexpr ET() : v() {
    CosT c;
    for (int s = 0; s < 2048; s++)
      for (int j = 0; j < 64; j++) {
        const int o = (s & 31) * 8192 + (s >> 5) * 64 + j;
        v[o] = c.v[(s * j) & 2047]; v[o + 4096] = c.v[(s * j + 512) & 2047];
      }
  }
};
struct alignas(1024) DT {
  uint16_t v[64 * 64];
  constexpr DT() : v() {
    CosT c;
    for (int r = 0; r < 64; r++)
      for (int n = 0; n < 64; n++) {
        const int sg = r >> 1, s0 = (sg & ~6) | ((sg & 2) << 1) | ((sg & 4) >> 1), e = r & 1, f = n & 1;
        const int m = 64 * s0 * (n >> 1) + (e == f ? 0 : e ? -512 : 512);
        v[r * 64 + (((n >> 3) ^ (r & 7)) << 3) + (n & 7)] = c.v[m & 2047];
      }
  }
};
}

__device__ constexpr tbl::FT g_FT = tbl::FT();
__device__ constexpr tbl::ET g_ET = tbl::ET();
__device__ constexpr tbl::DT g_DT = tbl::DT();

struct alignas(1024) Work {
  unsigned epoch[132 * 8];
  unsigned cntX[8 * 32], cntT[8 * 32], cntP[128 * 32], cntW[32], cntH[32];
  alignas(16) float gate[16 * 128];
  alignas(16) uint2 Wh[2 * 2048];
  alignas(16) uint2 Ts[32 * 64];
  alignas(1024) uint16_t X[129 * 8192];
  alignas(1024) uint16_t T[32 * 64 * 512];
  alignas(1024) uint4 part[128 * 3 * 1024];
};
__device__ Work g_work;
#define PROF_EV(i) do {} while (0)
#define PROF_CK(i) do {} while (0)

__device__ __forceinline__ uint32_t smem_u32(const void* p) { return (uint32_t)__cvta_generic_to_shared(p); }
__device__ __forceinline__ void mbar_init(uint32_t bar, uint32_t cnt) { asm volatile("mbarrier.init.shared::cta.b64 [%0], %1;" ::"r"(bar), "r"(cnt)); }
__device__ __forceinline__ void mbar_expect_tx(uint32_t bar, uint32_t bytes) { asm volatile("mbarrier.arrive.expect_tx.shared::cta.b64 _, [%0], %1;" ::"r"(bar), "r"(bytes) : "memory"); }
__device__ __forceinline__ void mbar_arrive(uint32_t bar) { asm volatile("mbarrier.arrive.shared::cta.b64 _, [%0];" ::"r"(bar) : "memory"); }
__device__ __forceinline__ bool elect_one() {
  uint32_t p;
  asm volatile("{\n.reg .pred p;\nelect.sync _|p, 0xffffffff;\nselp.u32 %0, 1, 0, p;\n}" : "=r"(p));
  return p;
}
__device__ __forceinline__ void mbar_arrive_if(bool p, uint32_t bar) {
  asm volatile("{\n.reg .pred p;\nsetp.ne.b32 p, %1, 0;\n@p mbarrier.arrive.shared::cta.b64 _, [%0];\n}" ::"r"(bar), "r"((int)p) : "memory");
}
__device__ __forceinline__ void hint_add_if(bool p, unsigned* a) {
  asm volatile("{\n.reg .pred p;\nsetp.ne.b32 p, %1, 0;\n@p red.relaxed.gpu.global.add.u32 [%0], 1;\n}" ::"l"(a), "r"((int)p) : "memory");
}
__device__ __forceinline__ bool mbar_try(uint32_t bar, uint32_t parity) {
  uint32_t ok;
  asm volatile("{\n.reg .pred p;\nmbarrier.test_wait.parity.shared::cta.b64 p, [%1], %2;\nselp.u32 %0, 1, 0, p;\n}" : "=r"(ok) : "r"(bar), "r"(parity) : "memory");
  return ok;
}
__device__ __forceinline__ void mbar_wait(uint32_t bar, uint32_t parity) {
  asm volatile(
      "{\n.reg .pred p;\n.reg .u32 n;\nmov.u32 n, 0;\n"
      "W_LOOP:\nmbarrier.try_wait.parity.shared::cta.b64 p, [%0], %1;\n@p bra W_DONE;\n"
      "add.u32 n, n, 1;\nsetp.lt.u32 p, n, 0x40000;\n@p bra W_LOOP;\ntrap;\nW_DONE:\n}" ::"r"(bar), "r"(parity) : "memory");
}
__device__ __forceinline__ void bulk_load(uint32_t dst, const void* src, uint32_t bytes, uint32_t bar) {
  asm volatile("cp.async.bulk.shared::cluster.global.mbarrier::complete_tx::bytes [%0], [%1], %2, [%3];" ::"r"(dst), "l"(src), "r"(bytes), "r"(bar) : "memory");
}
__device__ __forceinline__ void spin_guard(uint32_t t0) { if ((uint32_t)clock() - t0 > (1u << 30)) __trap(); }
__device__ __forceinline__ float2 ld_x2(const float2* p) { float2 v; asm volatile("ld.relaxed.gpu.global.v2.f32 {%0,%1}, [%2];" : "=f"(v.x), "=f"(v.y) : "l"(p) : "memory"); return v; }
__device__ __forceinline__ void st_u2(uint2* p, uint32_t a, uint32_t b) { asm volatile("st.relaxed.gpu.global.v2.u32 [%0], {%1,%2};" ::"l"(p), "r"(a), "r"(b) : "memory"); }
__device__ __forceinline__ uint32_t ld_x1(const void* p) { uint32_t v; asm volatile("ld.relaxed.gpu.global.u32 %0, [%1];" : "=r"(v) : "l"(p) : "memory"); return v; }
__device__ __forceinline__ uint4 ld_x4(const void* p) { uint4 v; asm volatile("ld.relaxed.gpu.global.v4.u32 {%0,%1,%2,%3}, [%4];" : "=r"(v.x), "=r"(v.y), "=r"(v.z), "=r"(v.w) : "l"(p) : "memory"); return v; }
__device__ __forceinline__ uint32_t mapa(uint32_t a, uint32_t cta) { uint32_t r; asm volatile("mapa.shared::cluster.u32 %0, %1, %2;" : "=r"(r) : "r"(a), "r"(cta)); return r; }
__device__ __forceinline__ void stsm4t(uint32_t a, uint32_t r0, uint32_t r1, uint32_t r2, uint32_t r3) {
  asm volatile("stmatrix.sync.aligned.m8n8.x4.trans.shared.b16 [%0], {%1,%2,%3,%4};" ::"r"(a), "r"(r0), "r"(r1), "r"(r2), "r"(r3) : "memory");
}
__device__ __forceinline__ void hint_add(unsigned* p) { asm volatile("red.relaxed.gpu.global.add.u32 [%0], 1;" ::"l"(p) : "memory"); }
__device__ __forceinline__ void hint_wait(const unsigned* p, unsigned target) {
  const uint32_t t0 = (uint32_t)clock();
  while ((int)(ld_x1(p) - target) < 0) spin_guard(t0);
}
__device__ __forceinline__ void bulk_done_signal(unsigned* p) {
  asm volatile("cp.async.bulk.commit_group;\ncp.async.bulk.wait_group 0;\nfence.proxy.async.global;" ::: "memory");
  hint_add(p);
}
__device__ __forceinline__ void flag_wait(const unsigned* p, unsigned target) {
  hint_wait(p, target);
  asm volatile("fence.proxy.async.global;" ::: "memory");
}
__device__ __forceinline__ void tma2d(uint32_t dst, const CUtensorMap* m, uint32_t bar, int c0, int c1) {
  asm volatile("cp.async.bulk.tensor.2d.shared::cluster.global.mbarrier::complete_tx::bytes [%0], [%1, {%3, %4}], [%2];" ::"r"(dst), "l"(m), "r"(bar), "r"(c0), "r"(c1) : "memory");
}
__device__ __forceinline__ void tma3d(uint32_t dst, const CUtensorMap* m, uint32_t bar, int c0, int c1, int c2) {
  asm volatile("cp.async.bulk.tensor.3d.shared::cluster.global.mbarrier::complete_tx::bytes [%0], [%1, {%3, %4, %5}], [%2];" ::"r"(dst), "l"(m), "r"(bar), "r"(c0), "r"(c1), "r"(c2) : "memory");
}
__device__ __forceinline__ void tma4d(uint32_t dst, const CUtensorMap* m, uint32_t bar, int c0, int c1, int c2, int c3) {
  asm volatile("cp.async.bulk.tensor.4d.shared::cluster.global.mbarrier::complete_tx::bytes [%0], [%1, {%3, %4, %5, %6}], [%2];" ::"r"(dst), "l"(m), "r"(bar), "r"(c0), "r"(c1), "r"(c2), "r"(c3) : "memory");
}
__device__ __forceinline__ void wg_fence() { asm volatile("wgmma.fence.sync.aligned;" ::: "memory"); }
__device__ __forceinline__ void wg_commit() { asm volatile("wgmma.commit_group.sync.aligned;" ::: "memory"); }
template <int N> __device__ __forceinline__ void wg_wait() { asm volatile("wgmma.wait_group.sync.aligned %0;" ::"n"(N) : "memory"); }
template <int O, int N, int NN> __device__ __forceinline__ void fence_regs(float (&d)[NN]) {
#pragma unroll
  for (int i = 0; i < N; i++) asm volatile("" : "+f"(d[O + i])::"memory");
}
__device__ __forceinline__ uint32_t pack_bf16(float lo, float hi) {
  uint32_t r; asm("cvt.rn.bf16x2.f32 %0, %1, %2;" : "=r"(r) : "f"(hi), "f"(lo)); return r;
}
__device__ __forceinline__ uint32_t pack_pin(float lo, float hi) {
  uint32_t r; asm volatile("cvt.rn.bf16x2.f32 %0, %1, %2;" : "=r"(r) : "f"(hi), "f"(lo) : "memory"); return r;
}
__device__ __forceinline__ uint32_t add_bf2(uint32_t a, uint32_t b) { uint32_t r; asm("add.rn.bf16x2 %0, %1, %2;" : "=r"(r) : "r"(a), "r"(b)); return r; }
__device__ __forceinline__ float bf_lo(uint32_t u) { return __uint_as_float(u << 16); }
__device__ __forceinline__ float bf_hi(uint32_t u) { return __uint_as_float(u & 0xffff0000u); }

__device__ __forceinline__ uint64_t d128(uint32_t lo) { uint64_t d; asm("mov.b64 %0, {%1, 0x40000040};" : "=l"(d) : "r"(lo)); return d; }
__device__ __forceinline__ uint64_t d64(uint32_t lo) { uint64_t d; asm("mov.b64 %0, {%1, 0x80000020};" : "=l"(d) : "r"(lo)); return d; }
template<int O,int TB,int ACC,int NN> __device__ __forceinline__ void mma_ss64(float (&d)[NN], uint64_t da, uint64_t db, int sd = 0){
  if constexpr (ACC == 1) asm volatile("wgmma.mma_async.sync.aligned.m64n64k16.f32.bf16.bf16 {%0,%1,%2,%3,%4,%5,%6,%7,%8,%9,%10,%11,%12,%13,%14,%15,%16,%17,%18,%19,%20,%21,%22,%23,%24,%25,%26,%27,%28,%29,%30,%31}, %32, %33, 1, 1, 1, %35, %34;"
   : "+f"(d[O+0]), "+f"(d[O+1]), "+f"(d[O+2]), "+f"(d[O+3]), "+f"(d[O+4]), "+f"(d[O+5]), "+f"(d[O+6]), "+f"(d[O+7]), "+f"(d[O+8]), "+f"(d[O+9]), "+f"(d[O+10]), "+f"(d[O+11]), "+f"(d[O+12]), "+f"(d[O+13]), "+f"(d[O+14]), "+f"(d[O+15]), "+f"(d[O+16]), "+f"(d[O+17]), "+f"(d[O+18]), "+f"(d[O+19]), "+f"(d[O+20]), "+f"(d[O+21]), "+f"(d[O+22]), "+f"(d[O+23]), "+f"(d[O+24]), "+f"(d[O+25]), "+f"(d[O+26]), "+f"(d[O+27]), "+f"(d[O+28]), "+f"(d[O+29]), "+f"(d[O+30]), "+f"(d[O+31])
   : "l"(da), "l"(db), "n"(TB & 1), "n"(TB >> 1));
  else if constexpr (ACC == 0) asm volatile("wgmma.mma_async.sync.aligned.m64n64k16.f32.bf16.bf16 {%0,%1,%2,%3,%4,%5,%6,%7,%8,%9,%10,%11,%12,%13,%14,%15,%16,%17,%18,%19,%20,%21,%22,%23,%24,%25,%26,%27,%28,%29,%30,%31}, %32, %33, 0, 1, 1, %35, %34;"
   : "=f"(d[O+0]), "=f"(d[O+1]), "=f"(d[O+2]), "=f"(d[O+3]), "=f"(d[O+4]), "=f"(d[O+5]), "=f"(d[O+6]), "=f"(d[O+7]), "=f"(d[O+8]), "=f"(d[O+9]), "=f"(d[O+10]), "=f"(d[O+11]), "=f"(d[O+12]), "=f"(d[O+13]), "=f"(d[O+14]), "=f"(d[O+15]), "=f"(d[O+16]), "=f"(d[O+17]), "=f"(d[O+18]), "=f"(d[O+19]), "=f"(d[O+20]), "=f"(d[O+21]), "=f"(d[O+22]), "=f"(d[O+23]), "=f"(d[O+24]), "=f"(d[O+25]), "=f"(d[O+26]), "=f"(d[O+27]), "=f"(d[O+28]), "=f"(d[O+29]), "=f"(d[O+30]), "=f"(d[O+31])
   : "l"(da), "l"(db), "n"(TB & 1), "n"(TB >> 1));
  else asm volatile("{\n.reg .pred p;\nsetp.ne.b32 p, %36, 0;\nwgmma.mma_async.sync.aligned.m64n64k16.f32.bf16.bf16 {%0,%1,%2,%3,%4,%5,%6,%7,%8,%9,%10,%11,%12,%13,%14,%15,%16,%17,%18,%19,%20,%21,%22,%23,%24,%25,%26,%27,%28,%29,%30,%31}, %32, %33, p, 1, 1, %35, %34;\n}"
   : "+f"(d[O+0]), "+f"(d[O+1]), "+f"(d[O+2]), "+f"(d[O+3]), "+f"(d[O+4]), "+f"(d[O+5]), "+f"(d[O+6]), "+f"(d[O+7]), "+f"(d[O+8]), "+f"(d[O+9]), "+f"(d[O+10]), "+f"(d[O+11]), "+f"(d[O+12]), "+f"(d[O+13]), "+f"(d[O+14]), "+f"(d[O+15]), "+f"(d[O+16]), "+f"(d[O+17]), "+f"(d[O+18]), "+f"(d[O+19]), "+f"(d[O+20]), "+f"(d[O+21]), "+f"(d[O+22]), "+f"(d[O+23]), "+f"(d[O+24]), "+f"(d[O+25]), "+f"(d[O+26]), "+f"(d[O+27]), "+f"(d[O+28]), "+f"(d[O+29]), "+f"(d[O+30]), "+f"(d[O+31])
   : "l"(da), "l"(db), "n"(TB & 1), "n"(TB >> 1), "r"(sd));
}
template<int O,int TB,int ACC,int NN> __device__ __forceinline__ void mma_rs64(float (&d)[NN], uint32_t a0, uint32_t a1, uint32_t a2, uint32_t a3, uint64_t db, int sd = 0){
  if constexpr (ACC == 1) asm volatile("wgmma.mma_async.sync.aligned.m64n64k16.f32.bf16.bf16 {%0,%1,%2,%3,%4,%5,%6,%7,%8,%9,%10,%11,%12,%13,%14,%15,%16,%17,%18,%19,%20,%21,%22,%23,%24,%25,%26,%27,%28,%29,%30,%31}, {%32,%33,%34,%35}, %36, 1, 1, 1, %37;"
   : "+f"(d[O+0]), "+f"(d[O+1]), "+f"(d[O+2]), "+f"(d[O+3]), "+f"(d[O+4]), "+f"(d[O+5]), "+f"(d[O+6]), "+f"(d[O+7]), "+f"(d[O+8]), "+f"(d[O+9]), "+f"(d[O+10]), "+f"(d[O+11]), "+f"(d[O+12]), "+f"(d[O+13]), "+f"(d[O+14]), "+f"(d[O+15]), "+f"(d[O+16]), "+f"(d[O+17]), "+f"(d[O+18]), "+f"(d[O+19]), "+f"(d[O+20]), "+f"(d[O+21]), "+f"(d[O+22]), "+f"(d[O+23]), "+f"(d[O+24]), "+f"(d[O+25]), "+f"(d[O+26]), "+f"(d[O+27]), "+f"(d[O+28]), "+f"(d[O+29]), "+f"(d[O+30]), "+f"(d[O+31])
   : "r"(a0), "r"(a1), "r"(a2), "r"(a3), "l"(db), "n"(TB));
  else if constexpr (ACC == 0) asm volatile("wgmma.mma_async.sync.aligned.m64n64k16.f32.bf16.bf16 {%0,%1,%2,%3,%4,%5,%6,%7,%8,%9,%10,%11,%12,%13,%14,%15,%16,%17,%18,%19,%20,%21,%22,%23,%24,%25,%26,%27,%28,%29,%30,%31}, {%32,%33,%34,%35}, %36, 0, 1, 1, %37;"
   : "=f"(d[O+0]), "=f"(d[O+1]), "=f"(d[O+2]), "=f"(d[O+3]), "=f"(d[O+4]), "=f"(d[O+5]), "=f"(d[O+6]), "=f"(d[O+7]), "=f"(d[O+8]), "=f"(d[O+9]), "=f"(d[O+10]), "=f"(d[O+11]), "=f"(d[O+12]), "=f"(d[O+13]), "=f"(d[O+14]), "=f"(d[O+15]), "=f"(d[O+16]), "=f"(d[O+17]), "=f"(d[O+18]), "=f"(d[O+19]), "=f"(d[O+20]), "=f"(d[O+21]), "=f"(d[O+22]), "=f"(d[O+23]), "=f"(d[O+24]), "=f"(d[O+25]), "=f"(d[O+26]), "=f"(d[O+27]), "=f"(d[O+28]), "=f"(d[O+29]), "=f"(d[O+30]), "=f"(d[O+31])
   : "r"(a0), "r"(a1), "r"(a2), "r"(a3), "l"(db), "n"(TB));
  else asm volatile("{\n.reg .pred p;\nsetp.ne.b32 p, %38, 0;\nwgmma.mma_async.sync.aligned.m64n64k16.f32.bf16.bf16 {%0,%1,%2,%3,%4,%5,%6,%7,%8,%9,%10,%11,%12,%13,%14,%15,%16,%17,%18,%19,%20,%21,%22,%23,%24,%25,%26,%27,%28,%29,%30,%31}, {%32,%33,%34,%35}, %36, p, 1, 1, %37;\n}"
   : "+f"(d[O+0]), "+f"(d[O+1]), "+f"(d[O+2]), "+f"(d[O+3]), "+f"(d[O+4]), "+f"(d[O+5]), "+f"(d[O+6]), "+f"(d[O+7]), "+f"(d[O+8]), "+f"(d[O+9]), "+f"(d[O+10]), "+f"(d[O+11]), "+f"(d[O+12]), "+f"(d[O+13]), "+f"(d[O+14]), "+f"(d[O+15]), "+f"(d[O+16]), "+f"(d[O+17]), "+f"(d[O+18]), "+f"(d[O+19]), "+f"(d[O+20]), "+f"(d[O+21]), "+f"(d[O+22]), "+f"(d[O+23]), "+f"(d[O+24]), "+f"(d[O+25]), "+f"(d[O+26]), "+f"(d[O+27]), "+f"(d[O+28]), "+f"(d[O+29]), "+f"(d[O+30]), "+f"(d[O+31])
   : "r"(a0), "r"(a1), "r"(a2), "r"(a3), "l"(db), "n"(TB), "r"(sd));
}
template<int O,int TB,int ACC,int NN> __device__ __forceinline__ void mma_ss128(float (&d)[NN], uint64_t da, uint64_t db, int sd = 0){
  if constexpr (ACC == 1) asm volatile("wgmma.mma_async.sync.aligned.m64n128k16.f32.bf16.bf16 {%0,%1,%2,%3,%4,%5,%6,%7,%8,%9,%10,%11,%12,%13,%14,%15,%16,%17,%18,%19,%20,%21,%22,%23,%24,%25,%26,%27,%28,%29,%30,%31,%32,%33,%34,%35,%36,%37,%38,%39,%40,%41,%42,%43,%44,%45,%46,%47,%48,%49,%50,%51,%52,%53,%54,%55,%56,%57,%58,%59,%60,%61,%62,%63}, %64, %65, 1, 1, 1, %67, %66;"
   : "+f"(d[O+0]), "+f"(d[O+1]), "+f"(d[O+2]), "+f"(d[O+3]), "+f"(d[O+4]), "+f"(d[O+5]), "+f"(d[O+6]), "+f"(d[O+7]), "+f"(d[O+8]), "+f"(d[O+9]), "+f"(d[O+10]), "+f"(d[O+11]), "+f"(d[O+12]), "+f"(d[O+13]), "+f"(d[O+14]), "+f"(d[O+15]), "+f"(d[O+16]), "+f"(d[O+17]), "+f"(d[O+18]), "+f"(d[O+19]), "+f"(d[O+20]), "+f"(d[O+21]), "+f"(d[O+22]), "+f"(d[O+23]), "+f"(d[O+24]), "+f"(d[O+25]), "+f"(d[O+26]), "+f"(d[O+27]), "+f"(d[O+28]), "+f"(d[O+29]), "+f"(d[O+30]), "+f"(d[O+31]), "+f"(d[O+32]), "+f"(d[O+33]), "+f"(d[O+34]), "+f"(d[O+35]), "+f"(d[O+36]), "+f"(d[O+37]), "+f"(d[O+38]), "+f"(d[O+39]), "+f"(d[O+40]), "+f"(d[O+41]), "+f"(d[O+42]), "+f"(d[O+43]), "+f"(d[O+44]), "+f"(d[O+45]), "+f"(d[O+46]), "+f"(d[O+47]), "+f"(d[O+48]), "+f"(d[O+49]), "+f"(d[O+50]), "+f"(d[O+51]), "+f"(d[O+52]), "+f"(d[O+53]), "+f"(d[O+54]), "+f"(d[O+55]), "+f"(d[O+56]), "+f"(d[O+57]), "+f"(d[O+58]), "+f"(d[O+59]), "+f"(d[O+60]), "+f"(d[O+61]), "+f"(d[O+62]), "+f"(d[O+63])
   : "l"(da), "l"(db), "n"(TB & 1), "n"(TB >> 1));
  else if constexpr (ACC == 0) asm volatile("wgmma.mma_async.sync.aligned.m64n128k16.f32.bf16.bf16 {%0,%1,%2,%3,%4,%5,%6,%7,%8,%9,%10,%11,%12,%13,%14,%15,%16,%17,%18,%19,%20,%21,%22,%23,%24,%25,%26,%27,%28,%29,%30,%31,%32,%33,%34,%35,%36,%37,%38,%39,%40,%41,%42,%43,%44,%45,%46,%47,%48,%49,%50,%51,%52,%53,%54,%55,%56,%57,%58,%59,%60,%61,%62,%63}, %64, %65, 0, 1, 1, %67, %66;"
   : "=f"(d[O+0]), "=f"(d[O+1]), "=f"(d[O+2]), "=f"(d[O+3]), "=f"(d[O+4]), "=f"(d[O+5]), "=f"(d[O+6]), "=f"(d[O+7]), "=f"(d[O+8]), "=f"(d[O+9]), "=f"(d[O+10]), "=f"(d[O+11]), "=f"(d[O+12]), "=f"(d[O+13]), "=f"(d[O+14]), "=f"(d[O+15]), "=f"(d[O+16]), "=f"(d[O+17]), "=f"(d[O+18]), "=f"(d[O+19]), "=f"(d[O+20]), "=f"(d[O+21]), "=f"(d[O+22]), "=f"(d[O+23]), "=f"(d[O+24]), "=f"(d[O+25]), "=f"(d[O+26]), "=f"(d[O+27]), "=f"(d[O+28]), "=f"(d[O+29]), "=f"(d[O+30]), "=f"(d[O+31]), "=f"(d[O+32]), "=f"(d[O+33]), "=f"(d[O+34]), "=f"(d[O+35]), "=f"(d[O+36]), "=f"(d[O+37]), "=f"(d[O+38]), "=f"(d[O+39]), "=f"(d[O+40]), "=f"(d[O+41]), "=f"(d[O+42]), "=f"(d[O+43]), "=f"(d[O+44]), "=f"(d[O+45]), "=f"(d[O+46]), "=f"(d[O+47]), "=f"(d[O+48]), "=f"(d[O+49]), "=f"(d[O+50]), "=f"(d[O+51]), "=f"(d[O+52]), "=f"(d[O+53]), "=f"(d[O+54]), "=f"(d[O+55]), "=f"(d[O+56]), "=f"(d[O+57]), "=f"(d[O+58]), "=f"(d[O+59]), "=f"(d[O+60]), "=f"(d[O+61]), "=f"(d[O+62]), "=f"(d[O+63])
   : "l"(da), "l"(db), "n"(TB & 1), "n"(TB >> 1));
  else asm volatile("{\n.reg .pred p;\nsetp.ne.b32 p, %68, 0;\nwgmma.mma_async.sync.aligned.m64n128k16.f32.bf16.bf16 {%0,%1,%2,%3,%4,%5,%6,%7,%8,%9,%10,%11,%12,%13,%14,%15,%16,%17,%18,%19,%20,%21,%22,%23,%24,%25,%26,%27,%28,%29,%30,%31,%32,%33,%34,%35,%36,%37,%38,%39,%40,%41,%42,%43,%44,%45,%46,%47,%48,%49,%50,%51,%52,%53,%54,%55,%56,%57,%58,%59,%60,%61,%62,%63}, %64, %65, p, 1, 1, %67, %66;\n}"
   : "+f"(d[O+0]), "+f"(d[O+1]), "+f"(d[O+2]), "+f"(d[O+3]), "+f"(d[O+4]), "+f"(d[O+5]), "+f"(d[O+6]), "+f"(d[O+7]), "+f"(d[O+8]), "+f"(d[O+9]), "+f"(d[O+10]), "+f"(d[O+11]), "+f"(d[O+12]), "+f"(d[O+13]), "+f"(d[O+14]), "+f"(d[O+15]), "+f"(d[O+16]), "+f"(d[O+17]), "+f"(d[O+18]), "+f"(d[O+19]), "+f"(d[O+20]), "+f"(d[O+21]), "+f"(d[O+22]), "+f"(d[O+23]), "+f"(d[O+24]), "+f"(d[O+25]), "+f"(d[O+26]), "+f"(d[O+27]), "+f"(d[O+28]), "+f"(d[O+29]), "+f"(d[O+30]), "+f"(d[O+31]), "+f"(d[O+32]), "+f"(d[O+33]), "+f"(d[O+34]), "+f"(d[O+35]), "+f"(d[O+36]), "+f"(d[O+37]), "+f"(d[O+38]), "+f"(d[O+39]), "+f"(d[O+40]), "+f"(d[O+41]), "+f"(d[O+42]), "+f"(d[O+43]), "+f"(d[O+44]), "+f"(d[O+45]), "+f"(d[O+46]), "+f"(d[O+47]), "+f"(d[O+48]), "+f"(d[O+49]), "+f"(d[O+50]), "+f"(d[O+51]), "+f"(d[O+52]), "+f"(d[O+53]), "+f"(d[O+54]), "+f"(d[O+55]), "+f"(d[O+56]), "+f"(d[O+57]), "+f"(d[O+58]), "+f"(d[O+59]), "+f"(d[O+60]), "+f"(d[O+61]), "+f"(d[O+62]), "+f"(d[O+63])
   : "l"(da), "l"(db), "n"(TB & 1), "n"(TB >> 1), "r"(sd));
}
template<int O,int TB,int ACC,int NN> __device__ __forceinline__ void mma_rs128(float (&d)[NN], uint32_t a0, uint32_t a1, uint32_t a2, uint32_t a3, uint64_t db, int sd = 0){
  if constexpr (ACC == 1) asm volatile("wgmma.mma_async.sync.aligned.m64n128k16.f32.bf16.bf16 {%0,%1,%2,%3,%4,%5,%6,%7,%8,%9,%10,%11,%12,%13,%14,%15,%16,%17,%18,%19,%20,%21,%22,%23,%24,%25,%26,%27,%28,%29,%30,%31,%32,%33,%34,%35,%36,%37,%38,%39,%40,%41,%42,%43,%44,%45,%46,%47,%48,%49,%50,%51,%52,%53,%54,%55,%56,%57,%58,%59,%60,%61,%62,%63}, {%64,%65,%66,%67}, %68, 1, 1, 1, %69;"
   : "+f"(d[O+0]), "+f"(d[O+1]), "+f"(d[O+2]), "+f"(d[O+3]), "+f"(d[O+4]), "+f"(d[O+5]), "+f"(d[O+6]), "+f"(d[O+7]), "+f"(d[O+8]), "+f"(d[O+9]), "+f"(d[O+10]), "+f"(d[O+11]), "+f"(d[O+12]), "+f"(d[O+13]), "+f"(d[O+14]), "+f"(d[O+15]), "+f"(d[O+16]), "+f"(d[O+17]), "+f"(d[O+18]), "+f"(d[O+19]), "+f"(d[O+20]), "+f"(d[O+21]), "+f"(d[O+22]), "+f"(d[O+23]), "+f"(d[O+24]), "+f"(d[O+25]), "+f"(d[O+26]), "+f"(d[O+27]), "+f"(d[O+28]), "+f"(d[O+29]), "+f"(d[O+30]), "+f"(d[O+31]), "+f"(d[O+32]), "+f"(d[O+33]), "+f"(d[O+34]), "+f"(d[O+35]), "+f"(d[O+36]), "+f"(d[O+37]), "+f"(d[O+38]), "+f"(d[O+39]), "+f"(d[O+40]), "+f"(d[O+41]), "+f"(d[O+42]), "+f"(d[O+43]), "+f"(d[O+44]), "+f"(d[O+45]), "+f"(d[O+46]), "+f"(d[O+47]), "+f"(d[O+48]), "+f"(d[O+49]), "+f"(d[O+50]), "+f"(d[O+51]), "+f"(d[O+52]), "+f"(d[O+53]), "+f"(d[O+54]), "+f"(d[O+55]), "+f"(d[O+56]), "+f"(d[O+57]), "+f"(d[O+58]), "+f"(d[O+59]), "+f"(d[O+60]), "+f"(d[O+61]), "+f"(d[O+62]), "+f"(d[O+63])
   : "r"(a0), "r"(a1), "r"(a2), "r"(a3), "l"(db), "n"(TB));
  else if constexpr (ACC == 0) asm volatile("wgmma.mma_async.sync.aligned.m64n128k16.f32.bf16.bf16 {%0,%1,%2,%3,%4,%5,%6,%7,%8,%9,%10,%11,%12,%13,%14,%15,%16,%17,%18,%19,%20,%21,%22,%23,%24,%25,%26,%27,%28,%29,%30,%31,%32,%33,%34,%35,%36,%37,%38,%39,%40,%41,%42,%43,%44,%45,%46,%47,%48,%49,%50,%51,%52,%53,%54,%55,%56,%57,%58,%59,%60,%61,%62,%63}, {%64,%65,%66,%67}, %68, 0, 1, 1, %69;"
   : "=f"(d[O+0]), "=f"(d[O+1]), "=f"(d[O+2]), "=f"(d[O+3]), "=f"(d[O+4]), "=f"(d[O+5]), "=f"(d[O+6]), "=f"(d[O+7]), "=f"(d[O+8]), "=f"(d[O+9]), "=f"(d[O+10]), "=f"(d[O+11]), "=f"(d[O+12]), "=f"(d[O+13]), "=f"(d[O+14]), "=f"(d[O+15]), "=f"(d[O+16]), "=f"(d[O+17]), "=f"(d[O+18]), "=f"(d[O+19]), "=f"(d[O+20]), "=f"(d[O+21]), "=f"(d[O+22]), "=f"(d[O+23]), "=f"(d[O+24]), "=f"(d[O+25]), "=f"(d[O+26]), "=f"(d[O+27]), "=f"(d[O+28]), "=f"(d[O+29]), "=f"(d[O+30]), "=f"(d[O+31]), "=f"(d[O+32]), "=f"(d[O+33]), "=f"(d[O+34]), "=f"(d[O+35]), "=f"(d[O+36]), "=f"(d[O+37]), "=f"(d[O+38]), "=f"(d[O+39]), "=f"(d[O+40]), "=f"(d[O+41]), "=f"(d[O+42]), "=f"(d[O+43]), "=f"(d[O+44]), "=f"(d[O+45]), "=f"(d[O+46]), "=f"(d[O+47]), "=f"(d[O+48]), "=f"(d[O+49]), "=f"(d[O+50]), "=f"(d[O+51]), "=f"(d[O+52]), "=f"(d[O+53]), "=f"(d[O+54]), "=f"(d[O+55]), "=f"(d[O+56]), "=f"(d[O+57]), "=f"(d[O+58]), "=f"(d[O+59]), "=f"(d[O+60]), "=f"(d[O+61]), "=f"(d[O+62]), "=f"(d[O+63])
   : "r"(a0), "r"(a1), "r"(a2), "r"(a3), "l"(db), "n"(TB));
  else asm volatile("{\n.reg .pred p;\nsetp.ne.b32 p, %70, 0;\nwgmma.mma_async.sync.aligned.m64n128k16.f32.bf16.bf16 {%0,%1,%2,%3,%4,%5,%6,%7,%8,%9,%10,%11,%12,%13,%14,%15,%16,%17,%18,%19,%20,%21,%22,%23,%24,%25,%26,%27,%28,%29,%30,%31,%32,%33,%34,%35,%36,%37,%38,%39,%40,%41,%42,%43,%44,%45,%46,%47,%48,%49,%50,%51,%52,%53,%54,%55,%56,%57,%58,%59,%60,%61,%62,%63}, {%64,%65,%66,%67}, %68, p, 1, 1, %69;\n}"
   : "+f"(d[O+0]), "+f"(d[O+1]), "+f"(d[O+2]), "+f"(d[O+3]), "+f"(d[O+4]), "+f"(d[O+5]), "+f"(d[O+6]), "+f"(d[O+7]), "+f"(d[O+8]), "+f"(d[O+9]), "+f"(d[O+10]), "+f"(d[O+11]), "+f"(d[O+12]), "+f"(d[O+13]), "+f"(d[O+14]), "+f"(d[O+15]), "+f"(d[O+16]), "+f"(d[O+17]), "+f"(d[O+18]), "+f"(d[O+19]), "+f"(d[O+20]), "+f"(d[O+21]), "+f"(d[O+22]), "+f"(d[O+23]), "+f"(d[O+24]), "+f"(d[O+25]), "+f"(d[O+26]), "+f"(d[O+27]), "+f"(d[O+28]), "+f"(d[O+29]), "+f"(d[O+30]), "+f"(d[O+31]), "+f"(d[O+32]), "+f"(d[O+33]), "+f"(d[O+34]), "+f"(d[O+35]), "+f"(d[O+36]), "+f"(d[O+37]), "+f"(d[O+38]), "+f"(d[O+39]), "+f"(d[O+40]), "+f"(d[O+41]), "+f"(d[O+42]), "+f"(d[O+43]), "+f"(d[O+44]), "+f"(d[O+45]), "+f"(d[O+46]), "+f"(d[O+47]), "+f"(d[O+48]), "+f"(d[O+49]), "+f"(d[O+50]), "+f"(d[O+51]), "+f"(d[O+52]), "+f"(d[O+53]), "+f"(d[O+54]), "+f"(d[O+55]), "+f"(d[O+56]), "+f"(d[O+57]), "+f"(d[O+58]), "+f"(d[O+59]), "+f"(d[O+60]), "+f"(d[O+61]), "+f"(d[O+62]), "+f"(d[O+63])
   : "r"(a0), "r"(a1), "r"(a2), "r"(a3), "l"(db), "n"(TB), "r"(sd));
}

#define NEARLY 0
#define XAHEAD 3
#define HEADN 6
#define WBATCH 1
#define WB 8
#define WSLEEP 20
#define XSPREAD 4
#define NOSEND 0
#define MSPLIT 2
#define PFALL 1
#define L2PF 0
#define STAG 0
#define EPF 2
#define XNB 2
#define FNB 0
#define GNB 0
#define TH 4
#define PF0 4
#define FSPLIT 1
#define MGLU 1
#define SPC 2
#define TL 14
#define GKB 4
#define T0A 7
#define T0B 11
#define TGATE 1
#define ZLATE 0
#define EARLYADD 0
#define OA 3
#define OB 11
#define EB 8
#define SPACE 100
#define WPF 1
#define WAFTER 7
#define WPACE 0
#define GATE_AT 4
#define TPACE 40
#define PFMODE 0
#define MAPMODE 1
template <int V> struct IC { static constexpr int value = V; };
struct Maps { CUtensorMap x, ft, g64, u64, e, wr, wi, xs, ts, t, g32, u32, d224, fg; };

constexpr int NCTA = 130;
constexpr int U = 16384;
constexpr int TB = 36864;
constexpr int OFF_RING = 8 * U, OFF_Z = 12 * U, OFF_XB = 12 * U, OFF_T = 13 * U, OFF_D = OFF_T;
constexpr int OFF_BAR = 14 * U, OFF_SP = OFF_BAR + 512, OFF_G = OFF_SP + 1024 + 128;
constexpr int SMEM_BYTES = OFF_G + 512;
constexpr int B_FX = 0, B_FA = 8, B_FT = 12, B_Z = 16, B_W = 24, B_HX = 25, B_TL = 26, B_HP = 27, B_WR = 31, B_E0 = 35;
constexpr int B_EA = 36, B_ET = 40, B_PZ = 44, B_RDY = 46, B_FE = 47, B_HF = 51;
constexpr int B_T = 53, B_XS = 54, B_G = 56, B_RD0 = 57, B_HS = 58, NBAR = 60;
__host__ __device__ constexpr int rslot(int n) { return n & 3; }
__host__ __device__ constexpr int rpar(int n) { return (n >> 2) & 1; }

__global__ void __cluster_dims__(2, 1, 1) __launch_bounds__(512, 1)
fused_kernel(Work* __restrict__ ws, const uint16_t* __restrict__ dtab, const __nv_bfloat16* __restrict__ w_r, const __nv_bfloat16* __restrict__ w_i,
             const __nv_bfloat16* __restrict__ gate_w, const __nv_bfloat16* __restrict__ x, __nv_bfloat16* __restrict__ out,
             const __grid_constant__ Maps maps) {
  extern __shared__ __align__(1024) uint8_t smem[];
  if (threadIdx.x < 32 && elect_one()) {
#pragma unroll
    for (int i = 0; i < PF0; i++) asm volatile("prefetch.tensormap [%0];" ::"l"((const char*)&maps + i * 128) : "memory");
  }
  const uint32_t sb = smem_u32(smem);
  const uint32_t bars = sb + OFF_BAR;
  const int tid = threadIdx.x, lane = tid & 31;
  const int warp = __shfl_sync(0xffffffffu, tid >> 5, 0);
  const bool helper = blockIdx.x >= 128;
  const int cl = (blockIdx.x >> 1) & 63, rank = blockIdx.x & 1;
  const int q4 = (cl & 1) | ((cl >> 2) & 2), rb = ((cl >> 1) & 3) | ((cl >> 4) << 2);
  const int j = 2 * q4 + rank;
  const int f_full = 448 * q4 + (rank ? 256 : 0);
  const int f_half = 448 * q4 + (rank ? 224 : 192);

  if (tid == 64) { PROF_EV(0); PROF_CK(40); }
  if (warp < 8) {
    if (!helper && tid < 32) {
      const int r = 16 * j + (tid & 15);
      asm volatile("prefetch.global.L2 [%0];" ::"l"(x + (size_t)(2 * rb + (r >> 6) + 32 * (r & 63)) * 512 + 64 * (tid >> 4)));
    }
    asm volatile("barrier.cluster.arrive.relaxed.aligned;" ::: "memory");
    asm volatile("setmaxnreg.inc.sync.aligned.u32 192;");
    if (!helper) {
      const int wg = warp >> 2, w = warp & 3, g = lane >> 2;
      const bool elect = (tid & 127) == 0;
      float cX[32], cA[64], cB[64], cC[64], ci[64], ct[64];
      const int zero = blockIdx.x >> 16;
      uint32_t h[56], yf[16];
      const uint32_t d0 = (sb & 0x3FFFF) >> 4;
      const uint32_t dK = d0 | (1u << 16), dN = d0 | (512u << 16);
      const uint32_t dX = dK + wg * 512;
      constexpr uint32_t RING = OFF_RING >> 4;
      auto waitA = [&](int n) { mbar_wait(bars + 8 * (B_FA + rslot(n)), rpar(n)); };
      auto freeA = [&](int n) { mbar_arrive_if(elect, bars + 8 * (B_EA + rslot(n))); };
      auto nop = [] {};

      asm volatile("bar.sync 0, 384;" ::: "memory");
#pragma unroll 1
      for (int i = 0; i < 4; i++) {
        const uint64_t dx = d128(dX + i * 2048), df = d128(dK + (OFF_XB >> 4) + (i & 1) * 1024);
        mbar_wait(bars + 8 * (B_FX + 2 * i), 0);
        wg_fence();
        mma_ss64<0, 0, 2>(cX, df, dx, i);
        mma_ss64<0, 0, 1>(cX, df + 2, dx + 2);
        wg_commit(); wg_wait<1>();
        mbar_arrive_if(elect && i, bars + 8 * (B_EA + rslot(i - 1)));
        mma_ss64<0, 0, 1>(cX, df + 4, dx + 4);
        mma_ss64<0, 0, 1>(cX, df + 6, dx + 6);
        if (i == 0 && tid == 0) PROF_EV(1);
        mbar_wait(bars + 8 * (B_FX + 2 * i + 1), 0);
        wg_fence();
#pragma unroll
        for (int k = 0; k < 4; k++) mma_ss64<0, 0, 1>(cX, df + (512 + k * 2), dx + (1024 + k * 2));
        wg_commit();
        waitA(i);
        wg_fence();
        const uint64_t da = d128(dX + i * 1024), db = d128(dN + RING + i * 1024);
        mma_ss128<0, 1, 2>(cA, da, db, i);
        wg_commit(); wg_wait<1>();
        mbar_arrive_if(elect, bars + 8 * (B_FE + i));
#pragma unroll
        for (int k = 1; k < 4; k++) mma_ss128<0, 1, 1>(cA, da + k * 2, db + k * 128);
        wg_commit();
      }
      fence_regs<0, 32>(cX);
#pragma unroll
      for (int e = 0; e < 16; e++) yf[e] = pack_pin(cX[2 * e], cX[2 * e + 1]);
      if (tid == 0) { PROF_EV(2); PROF_CK(42); }
      {
        waitA(4); mbar_wait(bars + 8 * B_E0, 0);
        const uint64_t de = d128(dN + (wg ? RING : OFF_XB >> 4));
        wg_fence();
        mma_rs128<0, 1, 0>(cB, yf[0], yf[1], yf[2], yf[3], de);
        wg_commit();
        wg_wait<1>();
        freeA(3);
#pragma unroll
        for (int k = 1; k < 4; k++) mma_rs128<0, 1, 1>(cB, yf[4 * k], yf[4 * k + 1], yf[4 * k + 2], yf[4 * k + 3], de + k * 128);
        wg_commit();
      }
      bool rel = false;
      auto acquire = [&](int n) {
        rel = elect;
        if (!mbar_try(bars + 8 * (B_FA + rslot(n)), rpar(n))) { wg_wait<0>(); freeA(n - 1); rel = false; waitA(n); }
      };
      auto freeP = [&](int n) { mbar_arrive_if(rel, bars + 8 * (B_EA + rslot(n - 1))); };
      auto ffn_step = [&](auto first, auto split, float (&acc)[64], int n, int kb, auto done, auto work) {
        constexpr int SPLIT = decltype(split)::value;
        acquire(n);
        wg_fence();
        const uint64_t dx = d128(dX + kb * 1024), db = d128(dN + RING + rslot(n) * 1024);
        mma_ss128<0, 1, decltype(first)::value>(acc, dx, db, kb);
#pragma unroll
        for (int k = 1; k < SPLIT; k++) mma_ss128<0, 1, 1>(acc, dx + k * 2, db + k * 128);
        wg_commit();
        work();
        wg_wait<1>();
        freeP(n);
        done();
        if (SPLIT < 4) {
          wg_fence();
#pragma unroll
          for (int k = SPLIT; k < 4; k++) mma_ss128<0, 1, 1>(acc, dx + k * 2, db + k * 128);
          wg_commit();
        }
      };
      {
        const int s0 = 2 * rb + wg, kr = 2 * ((s0 & 1) | ((s0 & 4) >> 1));
        const int m = lane >> 3, r = lane & 7;
        const uint32_t a0 = sb + OFF_XB + wg * 8192 + ((2 * (m >> 1) + (r >> 2)) * 2 + (w & 1)) * 256 + (m & 1) * 128 + (((2 * (r & 3) + ((w >> 1) ^ (r >> 2))) ^ (kr + (m & 1))) << 4);
        ffn_step(IC<1>(), IC<4>(), cA, 5, 4, [&] { fence_regs<0, 64>(cB); }, nop);
        asm volatile("bar.sync 5, 256;" ::: "memory");
        auto stage = [&](int i) {
          stsm4t(a0 + i * 2048, pack_bf16(cB[8 * i] - cB[34 + 8 * i], cB[8 * i + 1] - cB[35 + 8 * i]),
                 pack_bf16(cB[32 + 8 * i] + cB[8 * i + 2], cB[33 + 8 * i] + cB[8 * i + 3]),
                 pack_bf16(cB[8 * i + 4] - cB[38 + 8 * i], cB[8 * i + 5] - cB[39 + 8 * i]),
                 pack_bf16(cB[36 + 8 * i] + cB[8 * i + 6], cB[37 + 8 * i] + cB[8 * i + 7]));
          if (j == 0 && w == 0) {
            const uint32_t a1 = r ? sb + OFF_SP + 1024 : sb + OFF_SP + wg * 512 + (m & 1) * 256 + (m >> 1) * 128;
#pragma unroll
            for (int n = 2 * i; n < 2 * i + 2; n++)
              asm volatile("stmatrix.sync.aligned.m8n8.x4.shared.b16 [%0], {%1,%2,%3,%4};" ::"r"(a1 + ((n ^ (kr + (m >> 1)) ^ r) << 4)),
                           "r"(pack_bf16(cB[4 * n], cB[4 * n + 1])), "r"(pack_bf16(cB[4 * n + 2], cB[4 * n + 3])),
                           "r"(pack_bf16(cB[32 + 4 * n], cB[33 + 4 * n])), "r"(pack_bf16(cB[34 + 4 * n], cB[35 + 4 * n])) : "memory");
          }
        };
        auto publish = [&] {
          asm volatile("fence.proxy.async.shared::cta;" ::: "memory");
          __syncwarp();
          mbar_arrive_if(lane == 0, bars + 8 * (B_XS + wg));
          if (tid == 0) PROF_EV(3);
        };
        stage(0);
        ffn_step(IC<1>(), IC<FSPLIT>(), cA, 6, 5, nop, nop);
        stage(1);
        ffn_step(IC<1>(), IC<FSPLIT>(), cA, 7, 6, nop, nop);
        stage(2);
        ffn_step(IC<1>(), IC<2>(), cA, 8, 7, [&] { stage(3); }, nop);
        publish();
      }
      uint32_t gb0 = 0, gb1 = 0;
      uint32_t ob[2] = {0, 0};
      auto glu = [&](auto& acc, int half, int ho, int i0, int i1) {
#pragma unroll
        for (int i = i0; i < i1; i++)
          asm volatile("{\n.reg .b32 a, b;\ncvt.rn.relu.bf16x2.f32 a, %2, %1;\ncvt.rn.bf16x2.f32 b, %4, %3;\nmul.rn.bf16x2 a, a, b;\nmul.rn.bf16x2 %0, a, %5;\n}"
                       : "=r"(h[ho + i]) : "f"(acc[2 * i]), "f"(acc[2 * i + 1]), "f"(acc[half + 2 * i]), "f"(acc[half + 1 + 2 * i]), "r"(ob[i & 1]) : "memory");
      };
      ffn_step(IC<2>(), IC<1>(), cB, 9, zero, nop, nop);
#pragma unroll 1
      for (int kb = 1; kb < 8; kb++)
        ffn_step(IC<1>(), IC<FSPLIT>(), cB, 9 + kb, kb, nop, [&] {
          if (kb == GKB) {
            mbar_wait(bars + 8 * B_G, 0);
            asm volatile("ld.shared.u32 %0, [%2];\nld.shared.u32 %1, [%2+32];" : "=r"(gb0), "=r"(gb1) : "r"(sb + OFF_G + (wg * 64 + w * 16 + g) * 4) : "memory");
          } else if (kb == 5 + 2 * wg) {
            ob[0] = pack_bf16(1.0f - bf_hi(gb0), 1.0f - bf_hi(gb0)); ob[1] = pack_bf16(1.0f - bf_hi(gb1), 1.0f - bf_hi(gb1));
            glu(cA, 32, 0, 0, 16);
          }
        });
      const uint32_t tag = gb0 & 1;
      const float g0 = bf_hi(gb0), g1 = bf_hi(gb1);
      if (tid == 0) { PROF_EV(4); PROF_CK(43); }
      auto m_step = [&](auto first, int i) {
        acquire(17 + i);
        wg_fence();
        const uint64_t dx = d128(dX + i * 2048), dm = d64(dN + RING + rslot(17 + i) * 1024);
        mma_ss64<0, 1, decltype(first)::value>(ct, dx, dm);
#pragma unroll
        for (int k = 1; k < MSPLIT; k++) mma_ss64<0, 1, 1>(ct, dx + ((k >> 2) * 1024 + (k & 3) * 2), dm + k * 64);
        wg_commit();
        wg_wait<1>();
        freeP(17 + i);
        wg_fence();
#pragma unroll
        for (int k = MSPLIT; k < 8; k++) mma_ss64<0, 1, 1>(ct, dx + ((k >> 2) * 1024 + (k & 3) * 2), dm + k * 64);
        wg_commit();
      };
      m_step(IC<0>(), 0);
#pragma unroll 1
      for (int i = 1; i < 5; i++) {
        if (i == 1 + 2 * wg) glu(cB, 32, 16, 0, 16);
        if (i < 4) m_step(IC<1>(), i);
      }
      if (tid == 0) { PROF_EV(5); PROF_CK(44); }
      ffn_step(IC<0>(), IC<1>(), cC, 21, 0, nop, nop);
#pragma unroll 1
      for (int kb = 1; kb < 8; kb++)
        ffn_step(IC<1>(), IC<FSPLIT>(), cC, 21 + kb, kb, [&] { mbar_arrive_if(elect && !(kb & 1), bars + 8 * (B_ET + (kb >> 1) - 1)); }, [&] {
          if (kb == 1 + wg) glu(ct, 16, 48, 0, 8);
        });

      auto twait = [&](uint32_t bar, uint32_t par, int) { mbar_wait(bar, par); };
      auto tr = [] {};
      const int fo = warp * 128 + lane;
      auto fetch = [&](uint4 (&pv)[4], int z) {
        twait(bars + 8 * (z < 4 ? B_Z + 2 * z + wg : z < 6 ? B_HP + z - 4 : B_HP + 2 + wg), 0, 8 + z);
        const uint8_t* src = smem + (z < 4 ? OFF_Z - z * U : z == 4 ? OFF_T : (z - 5) * U) + fo * 16;
#pragma unroll
        for (int i = 0; i < 4; i++) pv[i] = *(const uint4*)(src + i * 512);
      };
      const uint32_t peerZ = mapa(sb + OFF_Z + fo * 16, rank ^ 1), peerB = mapa(bars + 8 * (B_Z + wg), rank ^ 1);
      auto tile_mma = [&](auto off, int t, int k0, int k1, bool fresh = false) {
        constexpr int O = decltype(off)::value;
        const uint64_t db = d128(dN + (t & 3) * (TB >> 4)), dw = db + rank * 256, dm = db + (rank ? 0 : 1536);
#pragma unroll
        for (int k = k0; k < k1; k++) {
          if (k == 0 && O == 0) mma_rs64<O, 1, 2>(ct, h[0], h[1], h[2], h[3], dw, zero);
          else if (k < 14) mma_rs64<O, 1, 1>(ct, h[4 * k], h[4 * k + 1], h[4 * k + 2], h[4 * k + 3], k < 12 ? dw + k * 128 : dm + (k - 12) * 128);
          else if (k == 14 && fresh) mma_rs64<O, 1, 0>(ct, yf[0], yf[1], yf[2], yf[3], db + k * 128);
          else if (k == 14) mma_rs64<O, 1, 2>(ct, yf[0], yf[1], yf[2], yf[3], db + k * 128, zero);
          else mma_rs64<O, 1, 1>(ct, yf[4 * k - 56], yf[4 * k - 55], yf[4 * k - 54], yf[4 * k - 53], db + k * 128);
        }
      };
      uint4 pv[4];
      const uint32_t sgn = rank ? 0x80008000u : 0u;
      auto even_end = [&](int t, int k0, bool fresh) {
        wg_fence();
        tile_mma(IC<32>(), t, 14, 18, fresh);
        wg_commit();
        tile_mma(IC<0>(), t, k0, 14);
        wg_commit();
        tr();
        wg_wait<1>();
        tr();
        fence_regs<32, 32>(ct);
#pragma unroll
        for (int i = 0; i < 4; i++)
          pv[i] = make_uint4(pack_pin(ct[32 + 8 * i], ct[33 + 8 * i]) ^ sgn, pack_pin(ct[34 + 8 * i], ct[35 + 8 * i]) ^ sgn,
                             pack_pin(ct[36 + 8 * i], ct[37 + 8 * i]) ^ sgn, pack_pin(ct[38 + 8 * i], ct[39 + 8 * i]) ^ sgn);
      };
      auto odd_head = [&](int t) {
        tr();
        twait(bars + 8 * (B_FT + (t & 3)), t >> 2, t);
        wg_fence();
        tile_mma(IC<32>(), t, 0, OA);
        wg_commit();
        tr();
        if (t < 4) twait(bars + 8 * (t == 1 ? B_RD0 : B_RDY), 0, 14 + t);
        wg_wait<1>();
        tr();
        mbar_arrive_if(elect && t < 6, bars + 8 * (B_ET + t - 1));
        fence_regs<0, 32>(ct);
        wg_fence();
#pragma unroll
        for (int i = 0; i < 4; i++) {
          asm volatile("st.async.weak.shared::cluster.mbarrier::complete_tx::bytes.v4.b32 [%0], {%2,%3,%4,%5}, [%1];" ::"r"(peerZ - (t >> 1) * U + i * 512),
                       "r"(peerB + 16 * (t >> 1)), "r"(add_bf2(pv[i].x, pack_bf16(ct[8 * i], ct[8 * i + 1]))), "r"(add_bf2(pv[i].y, pack_bf16(ct[8 * i + 2], ct[8 * i + 3]))),
                       "r"(add_bf2(pv[i].z, pack_bf16(ct[8 * i + 4], ct[8 * i + 5]))), "r"(add_bf2(pv[i].w, pack_bf16(ct[8 * i + 6], ct[8 * i + 7]))) : "memory");
          tile_mma(IC<32>(), t, OA + i, OA + i + 1);
        }
        wg_commit();
      };
      asm volatile("barrier.cluster.wait.aligned;" ::: "memory");
      twait(bars + 8 * B_FT, 0, 0);
      wg_fence();
      tile_mma(IC<0>(), 0, 0, T0A);
      wg_commit();
      waitA(29 + wg);
      wg_wait<1>();
      mbar_arrive_if(elect, bars + 8 * (B_ET + 3));
      glu(cC, 32, 32, 0, 16);
      if (tid == 0) PROF_EV(6);
      if (tid == 128) PROF_EV(27);
      mbar_wait(bars + 8 * (j == 0 ? B_T : B_TL), 0);
      if (tid == 0) { PROF_EV(7); PROF_CK(45); }
      wg_fence();
      {
        const uint64_t dt = d128(dN + (OFF_T >> 4) + wg * 512), de = d128(dK + RING + (1 + wg) * 1024);
        mma_ss64<0, 1, 0>(ci, de, dt);
        mma_ss64<32, 1, 0>(ci, de + 512, dt);
#pragma unroll
        for (int k = 1; k < 4; k++) {
          mma_ss64<0, 1, 1>(ci, de + k * 2, dt + k * 128);
          mma_ss64<32, 1, 1>(ci, de + (512 + k * 2), dt + k * 128);
        }
        wg_commit();
      }
      tile_mma(IC<0>(), 0, T0A, T0B);
      wg_commit();
      wg_wait<1>();
      if (elect) asm volatile("mbarrier.arrive.shared::cluster.b64 _, [%0];" ::"r"(mapa(bars + 8 * B_RDY, rank ^ 1)) : "memory");
      mbar_arrive_if(elect, bars + 8 * (B_PZ + 1));
      fence_regs<0, 64>(ci);
#pragma unroll
      for (int i = 0; i < 16; i++) {
        const float gg = ((i & 1) ? g1 : g0) * (2.0f / (2048.0f * 512.0f));
        if (i & 2) yf[i] = pack_pin((ci[2 * i] - ci[28 + 2 * i]) * gg, (ci[2 * i + 1] - ci[29 + 2 * i]) * gg);
        else yf[i] = pack_pin((ci[2 * i] + ci[36 + 2 * i]) * gg, (ci[2 * i + 1] + ci[37 + 2 * i]) * gg);
      }
      even_end(0, T0B, true);
      if (tid == 0) PROF_EV(8);
      if (tid == 128) PROF_EV(28);
#pragma unroll 1
      for (int t = 1; t < 7; t += 2) {
        odd_head(t);
        tr();
        wg_fence();
        tile_mma(IC<32>(), t, OA + 4, 14);
        wg_commit();
        tr();
        if (t == 5) fetch(pv, 2);
        twait(bars + 8 * (B_FT + ((t + 1) & 3)), (t + 1) >> 2, t + 1);
        wg_fence();
        tile_mma(IC<0>(), t + 1, 0, TH);
        wg_commit();
        if (t == 3) twait(bars + 8 * (B_HF + wg), 0, 20);
        tr();
        wg_wait<1>();
        tr();
        mbar_arrive_if(elect && t < 5, bars + 8 * (B_ET + t));
        fence_regs<32, 32>(ct);
        if (t == 5) {
          const int owner = rb * 8 + 2 * ((q4 + 3) & 3) + rank;
          uint4* dst = ws->part + (size_t)(owner * 3 + 2) * 1024 + fo;
#pragma unroll
          for (int i = 0; i < 4; i++)
            asm volatile("st.relaxed.gpu.global.v4.u32 [%0], {%1,%2,%3,%4};" ::"l"(dst + i * 32),
                         "r"((add_bf2(pv[i].x, pack_bf16(ct[32 + 8 * i], ct[33 + 8 * i])) & ~1u) | tag), "r"(add_bf2(pv[i].y, pack_bf16(ct[34 + 8 * i], ct[35 + 8 * i]))),
                         "r"(add_bf2(pv[i].z, pack_bf16(ct[36 + 8 * i], ct[37 + 8 * i]))), "r"(add_bf2(pv[i].w, pack_bf16(ct[38 + 8 * i], ct[39 + 8 * i]))) : "memory");
          hint_add_if(lane == 0, &ws->cntP[32 * owner + 8 * (2 + wg)]);
        } else {
#pragma unroll
        for (int i = 0; i < 4; i++)
          asm volatile("st.shared.v4.u32 [%0], {%1,%2,%3,%4};" ::"r"(sb + (1 + 2 * wg) * TB + 28672 + w * 2048 + i * 512 + lane * 16),
                       "r"(pack_bf16(ct[32 + 8 * i], ct[33 + 8 * i])), "r"(pack_bf16(ct[34 + 8 * i], ct[35 + 8 * i])),
                       "r"(pack_bf16(ct[36 + 8 * i], ct[37 + 8 * i])), "r"(pack_bf16(ct[38 + 8 * i], ct[39 + 8 * i])) : "memory");
        __syncwarp();
        mbar_arrive_if(lane == 0, bars + 8 * (B_HS + wg));
        }
        tr();
        wg_fence();
        tile_mma(IC<0>(), t + 1, TH, EB);
        wg_commit();
        tr();
        tr();
        even_end(t + 1, EB, false);
      }
      {
        uint4 p1[4], p2[4];
        auto acc4 = [&](uint4 (&d)[4], const uint4 (&a)[4]) {
#pragma unroll
          for (int i = 0; i < 4; i++) { d[i].x = add_bf2(d[i].x, a[i].x); d[i].y = add_bf2(d[i].y, a[i].y); d[i].z = add_bf2(d[i].z, a[i].z); d[i].w = add_bf2(d[i].w, a[i].w); }
        };
        auto add32 = [&](const uint4 (&a)[4]) {
#pragma unroll
          for (int i = 0; i < 4; i++) {
            const uint32_t u[4] = {a[i].x, a[i].y, a[i].z, a[i].w};
#pragma unroll
            for (int e = 0; e < 4; e++) { ct[32 + 8 * i + 2 * e] += bf_lo(u[e]); ct[33 + 8 * i + 2 * e] += bf_hi(u[e]); }
          }
        };
        odd_head(7);
        fetch(pv, 4);
        fetch(p1, 5);
        wg_fence();
        tile_mma(IC<32>(), 7, OA + 4, OB);
        wg_commit();
        uint32_t bad = 0;
#pragma unroll
        for (int i = 0; i < 4; i++) { bad |= (pv[i].x ^ tag) | (p1[i].x ^ tag); pv[i].x &= ~1u; p1[i].x &= ~1u; }
        acc4(pv, p1);
        fetch(p1, 3);
        wg_fence();
        tile_mma(IC<32>(), 7, OB, 14);
        wg_commit();
        if (tid == 0) { PROF_EV(9); PROF_CK(46); }
        if (tid == 128) PROF_EV(29);
        fetch(p2, 6);
        if (tid == 0) PROF_EV(24);
        wg_wait<0>();
        fence_regs<32, 32>(ct);
#pragma unroll
        for (int i = 0; i < 4; i++) bad |= p2[i].x ^ tag;
        if (__any_sync(0xffffffffu, bad & 1)) {
          const uint4* src = ws->part + (size_t)(rb * 8 + j) * 3 * 1024 + fo;
          uint4 p0[4];
          int n = 0;
          do {
            bad = 0;
#pragma unroll
            for (int i = 0; i < 4; i++) {
              pv[i] = ld_x4(src + i * 32); p0[i] = ld_x4(src + 1024 + i * 32); p2[i] = ld_x4(src + 2048 + i * 32);
              bad |= (pv[i].x ^ tag) | (p0[i].x ^ tag) | (p2[i].x ^ tag);
            }
            if (++n > (1 << 21)) __trap();
          } while (__any_sync(0xffffffffu, bad & 1));
#pragma unroll
          for (int i = 0; i < 4; i++) { pv[i].x &= ~1u; p0[i].x &= ~1u; }
          acc4(pv, p0);
        }
#pragma unroll
        for (int i = 0; i < 4; i++) p2[i].x &= ~1u;
        acc4(p1, p2);
        add32(pv); add32(p1);
#pragma unroll
        for (int i = 0; i < 4; i++)
          pv[i] = make_uint4(pack_bf16(ct[32 + 8 * i], ct[33 + 8 * i]), pack_bf16(ct[34 + 8 * i], ct[35 + 8 * i]), pack_bf16(ct[36 + 8 * i], ct[37 + 8 * i]), pack_bf16(ct[38 + 8 * i], ct[39 + 8 * i]));
        if (tid == 0) PROF_EV(14);
        const uint32_t stg = sb + OFF_T + warp * 2048;
        const int mr = (lane & 7) + ((lane >> 3) & 1) * 8, mc = lane >> 4;
#pragma unroll
        for (int i = 0; i < 4; i++)
          asm volatile("stmatrix.sync.aligned.m8n8.x4.shared.b16 [%0], {%1,%2,%3,%4};" ::"r"(stg + mr * 128 + (((2 * i + mc) ^ (mr & 7)) << 4)), "r"(pv[i].x),
                       "r"(pv[i].y), "r"(pv[i].z), "r"(pv[i].w) : "memory");
        __syncwarp();
#pragma unroll
        for (int i = 0; i < 4; i++) {
          const int r = 4 * i + (lane >> 3), c = lane & 7;
          const uint4 v = *(const uint4*)(smem + OFF_T + warp * 2048 + r * 128 + ((c ^ (r & 7)) << 4));
          *(uint4*)(out + (size_t)(2 * rb + wg + 32 * (16 * w + r)) * 512 + 64 * (q4 + 4 * rank) + 8 * c) = v;
        }
      }
      if (tid == 0) { PROF_EV(15); PROF_CK(41); }
      if (tid == 128) PROF_EV(30);
    }
  } else if (warp < 12) {
    asm volatile("setmaxnreg.dec.sync.aligned.u32 104;");
    asm volatile("barrier.cluster.arrive.relaxed.aligned;" ::: "memory");
    const int t = tid - 256, w = warp - 8;
    const uint32_t ep = ld_x1(&ws->epoch[blockIdx.x * 8]);
    const uint32_t tag = (ep + 1) & 1;
    auto w_issue = [&](const CUtensorMap* m) {

      if (elect_one()) { mbar_expect_tx(bars + 8 * (B_WR + w), 3072); tma4d(sb + OFF_T + w * 3072, m, bars + 8 * (B_WR + w), 32 * j, 0, 4 * (rb & 1) + w, rb >> 1); }

          __syncwarp();
    };
    auto gate_rows = [&] {
      const int r = 16 * j + 4 * w + (lane >> 3);
      const uint4* pg = (const uint4*)gate_w + (lane & 7);
      {
        float a = 0.f;
        asm volatile("bar.sync 4, 256;" ::: "memory");
#pragma unroll 1
        for (int hf = 0; hf < 2; hf++) {
          uint4 v[4], u[4];
#pragma unroll
          for (int kb = 0; kb < 4; kb++) v[kb] = __ldg(pg + (4 * hf + kb) * 8);
          mbar_wait(bars + 8 * (B_FE + 1 + 2 * hf), 0);
          if (hf) w_issue(&maps.wr);
#pragma unroll
          for (int kb = 0; kb < 4; kb++) u[kb] = *(const uint4*)(smem + (4 * hf + kb) * U + r * 128 + (((lane ^ r) & 7) << 4));
#pragma unroll
          for (int kb = 0; kb < 4; kb++) {
            const uint32_t uu[4] = {u[kb].x, u[kb].y, u[kb].z, u[kb].w}, vv[4] = {v[kb].x, v[kb].y, v[kb].z, v[kb].w};
#pragma unroll
            for (int e = 0; e < 4; e++) {
              uint32_t pr;
              asm("mul.rn.bf16x2 %0, %1, %2;" : "=r"(pr) : "r"(uu[e]), "r"(vv[e]));
              a += bf_lo(pr) + bf_hi(pr);
            }
          }
        }
#pragma unroll
        for (int o = 4; o; o >>= 1) a += __shfl_xor_sync(0xffffffffu, a, o);
        if ((lane & 7) == 0)
          asm volatile("st.relaxed.gpu.global.u32 [%0], %1;" ::"l"(ws->gate + rb * 128 + r),
                       "r"(pack_bf16(0.f, __fdividef(1.0f, 1.0f + __expf(-bf_lo(pack_bf16(a, 0.f))))) | tag) : "memory");
        if (t == 0) PROF_EV(18);
      }
    };
    {
      const int g = lane >> 2, q = lane & 3;
      uint32_t wf[32];
      if (!helper) {
        gate_rows();
        const uint32_t wa = sb + OFF_T + w * (3072 + 2) + (rb & 1) * 8 + q * 96 + g * 4, wb[2] = {wa + (rb & 1) * 32, wa + 32 - (rb & 1) * 32};
#pragma unroll 1
        for (int ri = 0; ri < 2; ri++) {
          mbar_wait(bars + 8 * (B_WR + w), ri);
#pragma unroll
          for (int n2 = 0; n2 < 32 / WB; n2++) {
            uint32_t v[WB];
#pragma unroll
            for (int i = 0; i < WB; i++) {
              const int e = n2 * WB + i;
              asm volatile("ld.shared.u16 %0, [%1];" : "=r"(v[i]) : "r"(wb[e & 1] + ((e >> 1) & 7) * 384 + (e >> 4) * 2) : "memory");
            }
#pragma unroll
            for (int i = 0; i < WB; i++) wf[n2 * WB + i] = __byte_perm(wf[n2 * WB + i], v[i], 0x5432);
            if (WSLEEP) { asm volatile("nanosleep.u32 %0;" ::"r"(WSLEEP + (v[WB - 1] >> 16)) : "memory"); }
          }
          __syncwarp();
          if (ri == 0) w_issue(&maps.wi);
        }
        asm volatile("bar.sync 1, 128;" ::: "memory");
        if (t == 0) PROF_EV(11);
      } else {
        asm volatile("bar.sync 4, 256;" ::: "memory");
        hint_wait(&ws->cntW[0], (ep + 1) * 128u);
        const uint32_t t0 = (uint32_t)clock();
#pragma unroll 1
        for (;;) {
          uint32_t bad = 0;
#pragma unroll
          for (int i = 0; i < 32; i++) {
            const float2 v = ld_x2((const float2*)ws->Wh + (i >> 4) * 2048 + 16 * w + g + 8 * (i & 1) + 64 * q + ((i >> 1) & 7) * 256);
            wf[i] = __float_as_uint(v.x); bad |= __float_as_uint(v.y) ^ tag;
          }
          if (!__any_sync(0xffffffffu, bad & 1)) break;
          spin_guard(t0);
        }
        if (t == 0) PROF_EV(11);
      }
      if (w == 0 && elect_one()) { mbar_expect_tx(bars + 8 * B_W, 8192); bulk_load(sb + OFF_D, dtab, 8192, bars + 8 * B_W); }
      asm volatile("barrier.cluster.wait.aligned;" ::: "memory");
      mbar_wait(bars + 8 * B_W, 0);
      mbar_wait(bars + 8 * B_HX, 0);
      if (t == 0) PROF_EV(12);
      const uint32_t dd = (sb & 0x3FFFF) >> 4;
      const uint64_t dF = d128((dd + (OFF_D >> 4)) | (512u << 16)), dI = d128((dd + (OFF_D >> 4)) | (1u << 16)), dA = d128((dd + (OFF_XB >> 4)) | (512u << 16));
      float az[32];
      const int zero = blockIdx.x >> 16;
      uint32_t pf[32];
#pragma unroll
      for (int mt = 0; mt < 2; mt++) {
        wg_fence();
        if (mt == 0) mma_ss64<0, 3, 0>(az, dA, dF);
        else mma_ss64<0, 3, 2>(az, dA + 512, dF, zero);
#pragma unroll
        for (int k = 1; k < 4; k++) mma_ss64<0, 3, 1>(az, dA + (mt * 512 + k * 128), dF + k * 128);
        wg_commit();
        wg_wait<0>();
        fence_regs<0, 32>(az);
#pragma unroll
        for (int i = 0; i < 16; i++) {
          const float wr = bf_lo(wf[16 * mt + i]), wi = bf_hi(wf[16 * mt + i]);
          pf[16 * mt + i] = pack_pin(fmaf(az[2 * i], wr, -az[2 * i + 1] * wi), fmaf(az[2 * i], wi, az[2 * i + 1] * wr));
        }
      }
      if (t == 0) PROF_EV(16);
      {
        const int m = lane >> 3, r = lane & 7;
        const int sl = 2 * (m >> 1) + ((r >> 1) & 1) + 4 * (r >> 2);
        const uint32_t a0 = sb + OFF_XB + w * 4096 + sl * 64 + (((((m ^ rb) & 1) * 2 + (r & 1)) ^ (sl >> 1)) << 4);
        uint32_t pk[16];
#pragma unroll
        for (int mt = 0; mt < 3; mt++) {
          if (mt < 2) {
            wg_fence();
            mma_rs64<0, 0, 2>(az, pf[16 * mt], pf[16 * mt + 1], pf[16 * mt + 2], pf[16 * mt + 3], dI, mt ? (int)helper : zero);
#pragma unroll
            for (int k = 1; k < 4; k++) mma_rs64<0, 0, 1>(az, pf[16 * mt + 4 * k], pf[16 * mt + 4 * k + 1], pf[16 * mt + 4 * k + 2], pf[16 * mt + 4 * k + 3], dI + k * 2);
            wg_commit();
          }
          if (mt > 0 && !helper) {
#pragma unroll
            for (int i = 0; i < 4; i++) stsm4t(a0 + (mt - 1) * 2048 + i * 512, pk[4 * i], pk[4 * i + 1], pk[4 * i + 2], pk[4 * i + 3]);
          }
          if (mt < 2) {
            wg_wait<0>();
            fence_regs<0, 32>(az);
#pragma unroll
            for (int i = 0; i < 16; i++) pk[i] = pack_pin(az[2 * i], az[2 * i + 1]);
          }
        }
      }
      if (helper) {
#pragma unroll
        for (int i = 0; i < 16; i++) {
          const int n = i >> 1, s0 = 8 * (n >> 1) + 2 * (n & 1) + (q & 1) + 4 * (q >> 1);
          if ((n & 1) == (int)(blockIdx.x & 1)) st_u2(ws->Ts + s0 * 64 + 16 * w + g + 8 * (i & 1), pack_bf16(az[2 * i], az[2 * i + 1]), tag);
        }
        __syncwarp();
        hint_add_if(lane == 0, &ws->cntH[0]);
        if (t == 0) { ws->epoch[blockIdx.x * 8] = ep + 1; PROF_EV(13); }
      } else {
        asm volatile("fence.proxy.async.shared::cta;" ::: "memory");
        __syncwarp();
        if (elect_one()) {
          if (t == 0) PROF_EV(17);
          if (SPACE) __nanosleep(SPACE * w);
          asm volatile("cp.async.bulk.tensor.4d.global.shared::cta.bulk_group [%0, {%2, %3, %4, %5}], [%1];" ::"l"(&maps.ts), "r"(sb + OFF_XB + w * 4096),
                       "r"(32 * rank), "r"(0), "r"(2 * q4), "r"(4 * rb + w) : "memory");
          bulk_done_signal(&ws->cntT[32 * q4]);
          asm volatile("mbarrier.arrive.shared::cluster.b64 _, [%0];" ::"r"(mapa(bars + 8 * B_RD0, rank ^ 1)) : "memory");
          if (t == 96) PROF_EV(13);
        }
        __syncwarp();
        if (j == 0) {
          hint_wait(&ws->cntH[0], (ep + 1) * 8u);
          const uint32_t t0 = (uint32_t)clock();
          float2 v;
          do { v = ld_x2((const float2*)ws->Ts + 2 * rb * 64 + t); spin_guard(t0); } while (__any_sync(0xffffffffu, (__float_as_uint(v.y) ^ tag) & 1));
          mbar_wait(bars + 8 * B_TL, 0);
          const uint32_t u = __float_as_uint(v.x);
          *(uint16_t*)(smem + OFF_T + t * 128 + ((t & 7) << 4)) = (uint16_t)u;
          *(uint16_t*)(smem + OFF_T + t * 128 + (((t & 7) ^ 1) << 4)) = (uint16_t)(u >> 16);
          asm volatile("fence.proxy.async.shared::cta;" ::: "memory");
          __syncwarp();
          mbar_arrive_if(lane == 0, bars + 8 * B_T);
        }
        const int hw = w >> 1;
#pragma unroll 1
        for (int z = 0; z < 2; z++) {
          const int owner = rb * 8 + 2 * ((q4 + z + 1) & 3) + rank;
          uint4* dst = ws->part + (size_t)(owner * 3 + z) * 1024 + w * 256 + lane;
          const uint8_t* pa = smem + (1 + 2 * hw) * TB + 28672 + (w & 1) * 4096 + lane * 16;
          const uint8_t* pb = smem + OFF_Z - z * U + w * 4096 + lane * 16;
          uint4 a[8], b[8];
          mbar_wait(bars + 8 * (B_Z + 2 * z + hw), 0);
#pragma unroll
          for (int i = 0; i < 8; i++) b[i] = *(const uint4*)(pb + i * 512);
          mbar_wait(bars + 8 * (B_HS + hw), z & 1);
#pragma unroll
          for (int i = 0; i < 8; i++) a[i] = *(const uint4*)(pa + i * 512);
#pragma unroll
          for (int i = 0; i < 8; i++)
            asm volatile("st.relaxed.gpu.global.v4.u32 [%0], {%1,%2,%3,%4};" ::"l"(dst + i * 32), "r"((add_bf2(a[i].x, b[i].x) & ~1u) | tag),
                         "r"(add_bf2(a[i].y, b[i].y)), "r"(add_bf2(a[i].z, b[i].z)), "r"(add_bf2(a[i].w, b[i].w)) : "memory");
          hint_add_if(lane == 0, &ws->cntP[32 * owner + 8 * z]);
          __syncwarp();
          mbar_arrive_if(lane == 0, bars + 8 * (B_HF + hw));
        }
      }
    }
  } else {
    asm volatile("setmaxnreg.dec.sync.aligned.u32 24;");
    auto xf_load = [&](int q) {
      const uint32_t fb = bars + 8 * (B_FX + q);
      mbar_expect_tx(fb, U + 8192);
      tma3d(sb + q * U, &maps.x, fb, 64 * q, 0, 2 * rb);
      if (q >= 4) mbar_wait(bars + 8 * (B_FE + ((q - 4) >> 1)), 0);
      tma2d(sb + OFF_XB + (q & 3) * 8192, &maps.ft, fb, 64 * q, 64 * j);
    };
    if (elect_one()) {
      if (warp == 14) {
#pragma unroll
        for (int i = 0; i < B_FT; i++) mbar_init(bars + 8 * i, 1);
        asm volatile("fence.mbarrier_init.release.cluster;" ::: "memory");
        if (!helper) {
#pragma unroll 1
          for (int n = 0; n < 2; n++) {
            const uint32_t fb = bars + 8 * (B_FA + n);
            xf_load(2 * n); xf_load(2 * n + 1);
            mbar_expect_tx(fb, U);
            tma2d(sb + OFF_RING + n * U, &maps.g64, fb, f_full, 64 * n);
            tma2d(sb + OFF_RING + n * U + 8192, &maps.u64, fb, f_full, 64 * n);
          }
        }
      } else if (warp == 15) {
#pragma unroll
        for (int i = B_FT; i < NBAR; i++) mbar_init(bars + 8 * i, i < B_EA ? 1 : i < B_T ? 2 : 4);
#pragma unroll
        for (int i = 0; i < 8; i++) mbar_expect_tx(bars + 8 * (B_Z + i), U / 2);
        asm volatile("fence.mbarrier_init.release.cluster;" ::: "memory");
        asm volatile("fence.proxy.async.shared::cta;" ::: "memory");
      }
    }
    __syncwarp();
    asm volatile("bar.arrive 0, 384;" ::: "memory");
    asm volatile("bar.arrive 4, 256;" ::: "memory");
    __syncwarp();
    asm volatile("barrier.cluster.arrive.relaxed.aligned;" ::: "memory");
    asm volatile("bar.sync 3, 128;" ::: "memory");
    if (warp == 15 && !helper) {
        mbar_wait(bars + 8 * B_FE, 0);
        const uint32_t tag = (ld_x1(&ws->epoch[blockIdx.x * 8]) + 1) & 1;
        const int c = lane >> 4, jj = 16 * blockIdx.x + (lane & 15), jm = (2048 - jj) & 2047;
        const unsigned short* pr = (const unsigned short*)w_r + 256 * c;
        const unsigned short* pi = (const unsigned short*)w_i + 256 * c;
        const float wr = 0.25f * (bf_lo(__ldg(pr + jj * 257)) + bf_lo(__ldg(pr + jm * 257)));
        const float wi = 0.25f * (bf_lo(__ldg(pi + jj * 257)) - bf_lo(__ldg(pi + jm * 257)));
        st_u2(ws->Wh + c * 2048 + jj, c ? pack_bf16(-wi, wr) : pack_bf16(wr, wi), tag);
        __syncwarp();
        hint_add_if(lane == 0, &ws->cntW[0]);
        mbar_wait(bars + 8 * B_XS, 0);
        const uint32_t t0 = (uint32_t)clock();
        uint4 v;
        do { v = ld_x4(ws->gate + rb * 128 + 4 * lane); spin_guard(t0); } while (__any_sync(0xffffffffu, ((v.x ^ tag) | (v.y ^ tag) | (v.z ^ tag) | (v.w ^ tag)) & 1));
        *(uint4*)(smem + OFF_G + lane * 16) = v;
        __syncwarp();
        mbar_arrive_if(lane < 4, bars + 8 * B_G);
      }
    auto part_load = [&](int i, unsigned ep1) {
      const uint32_t bytes = i < 2 ? U : U / 2;
      mbar_wait(bars + 8 * (B_PZ + (i == 0)), 0);
      mbar_expect_tx(bars + 8 * (B_HP + i), bytes);
      flag_wait(&ws->cntP[32 * (rb * 8 + j) + 8 * i], ep1 * 4u);
      bulk_load(sb + (i == 0 ? OFF_T : i == 1 ? 0 : i * (U / 2)), ws->part + (size_t)(rb * 8 + j) * 3072 + (i < 2 ? i * 1024 : 1024 + i * 512), bytes, bars + 8 * (B_HP + i));
      if (i == 2) PROF_EV(26);
    };
    if ((!helper || warp == 15) && elect_one()) {
      if (warp < 14) {
        const int p = warp - 12;
#pragma unroll 1
        for (int i = 4 + p; i < 14; i += 2) asm volatile("prefetch.tensormap [%0];" ::"l"((const char*)&maps + i * 128) : "memory");
#pragma unroll 1
        for (int n = 2; n < 31; n++) {
          const bool table = n == 4 || n >= 29;
          const bool half = n >= 17 && n < 21;
          const int q = n < 4 ? n : n < 17 ? n - 1 : n - 5;
          const CUtensorMap* m = table ? &maps.e : half ? &maps.g32 + p : &maps.g64 + p;
          const int c0 = table ? 0 : half ? f_half : f_full + 64 * (q >> 3);
          const int c1 = table ? (2 * rb + ((n & 1) ^ 1)) * 128 + 64 * p : half ? 128 * (n - 17) : 64 * (q & 7);
          const uint32_t fb = bars + 8 * (B_FA + (n & 3)), dst = sb + OFF_RING + (n & 3) * U + p * 8192;
          if (n < 4) mbar_wait(bars + 8 * (B_FE + n - 2), 0);
          else mbar_wait(bars + 8 * (B_EA + (n & 3)), ((n >> 2) & 1) ^ 1);
          tma2d(dst, m, fb, c0, c1);
          if (p == 0) mbar_expect_tx(fb, U);
        }
        part_load(2 + p, ld_x1(&ws->epoch[blockIdx.x * 8]) + 1);
      } else if (warp == 15) {
        const unsigned ep1 = ld_x1(&ws->epoch[blockIdx.x * 8]) + 1;
        flag_wait(&ws->cntX[helper ? 0 : 32 * j], ep1 * 16u);
        PROF_EV(22);
        mbar_expect_tx(bars + 8 * B_HX, U);
        bulk_load(sb + OFF_XB, ws->X + (size_t)(helper ? 128 : 16 * j + rb) * 8192, U, bars + 8 * B_HX);
        if (!helper) {
          flag_wait(&ws->cntT[32 * q4], ep1 * 128u);
          PROF_EV(23);
          mbar_expect_tx(bars + 8 * B_TL, U);
          tma3d(sb + OFF_T, &maps.t, bars + 8 * B_TL, 64 * j, 0, 2 * rb);
          part_load(0, ep1); part_load(1, ep1);
          mbar_wait(bars + 8 * (B_HP + 2), 0); mbar_wait(bars + 8 * (B_HP + 3), 0);
          ws->epoch[blockIdx.x * 8] = ep1;
        }
      } else {
#pragma unroll 1
        for (int q = 4; q < 8; q++) xf_load(q);
        mbar_wait(bars + 8 * (B_FE + 2), 0);
        mbar_expect_tx(bars + 8 * B_E0, U);
        tma2d(sb + OFF_XB, &maps.e, bars + 8 * B_E0, 0, 2 * rb * 128);
        tma2d(sb + OFF_XB + 8192, &maps.e, bars + 8 * B_E0, 0, 2 * rb * 128 + 64);
#pragma unroll 1
        for (int h2 = 0; h2 < 2; h2++) {
          const int s0 = 2 * rb + h2, sg = (s0 & ~6) | ((s0 & 2) << 1) | ((s0 & 4) >> 1);
          mbar_wait(bars + 8 * (B_XS + h2), 0);
#pragma unroll 1
          for (int c = 0; c < 2; c++) {
            asm volatile("cp.async.bulk.tensor.4d.global.shared::cta.bulk_group [%0, {%2, %3, %4, %5}], [%1];" ::"l"(&maps.xs),
                         "r"(sb + OFF_XB + h2 * 8192 + c * 4096), "r"(0), "r"(sg), "r"(0), "r"(16 * j + 8 * c) : "memory");
            if (j == 0)
              asm volatile("cp.async.bulk.global.shared::cta.bulk_group [%0], [%1], 256;" ::"l"(ws->X + 128 * 8192 + c * 4096 + sg * 128),
                           "r"(sb + OFF_SP + h2 * 512 + c * 256) : "memory");
            if (SPACE && h2 + c < 2) __nanosleep(SPACE);
          }
        }
        bulk_done_signal(&ws->cntX[32 * j]);
        PROF_EV(20);
#pragma unroll 1
        for (int t = 0; t < 8; t++) {
          const int col = 64 * (((q4 + 1 + (t >> 1)) & 3) + 4 * ((t & 1) ? rank : 1 - rank));
          const uint32_t fb = bars + 8 * (B_FT + (t & 3)), dst = sb + (t & 3) * TB;
          mbar_wait(bars + 8 * (B_ET + (t < 3 ? t + 1 : t & 3)), t >> 2);
          mbar_expect_tx(fb, (t & 1) ? 28672 : TB);
          tma2d(dst, &maps.d224, fb, col, 224 * j);
          if (!(t & 1)) tma3d(dst + 28672, &maps.fg, fb, col ^ 256, 16 * rank, 4 * q4);
        }
      }
    }
  }
}

typedef CUresult (*EncodeFn)(CUtensorMap*, CUtensorMapDataType, cuuint32_t, void*, const cuuint64_t*, const cuuint64_t*, const cuuint32_t*,
                             const cuuint32_t*, CUtensorMapInterleave, CUtensorMapSwizzle, CUtensorMapL2promotion, CUtensorMapFloatOOBfill);

static void encode(EncodeFn f, CUtensorMap* m, const void* base, int rank, const cuuint64_t* dims, const cuuint64_t* strides, const cuuint32_t* box,
                   CUtensorMapSwizzle sw) {
  cuuint32_t es[5] = {1, 1, 1, 1, 1};
  f(m, CU_TENSOR_MAP_DATA_TYPE_BFLOAT16, rank, (void*)base, dims, strides, box, es, CU_TENSOR_MAP_INTERLEAVE_NONE, sw,
    CU_TENSOR_MAP_L2_PROMOTION_L2_128B, CU_TENSOR_MAP_FLOAT_OOB_FILL_NONE);
}

extern "C" void kernel_launch(void* const* d_in, const int* in_sizes, int n_in, void* d_out, int out_size) {
  (void)in_sizes; (void)n_in; (void)out_size;
  const __nv_bfloat16* x = (const __nv_bfloat16*)d_in[0];
  const __nv_bfloat16* w_r = (const __nv_bfloat16*)d_in[1];
  const __nv_bfloat16* w_i = (const __nv_bfloat16*)d_in[2];
  const __nv_bfloat16* Wg = (const __nv_bfloat16*)d_in[4];
  const __nv_bfloat16* Wu = (const __nv_bfloat16*)d_in[5];
  const __nv_bfloat16* Wd = (const __nv_bfloat16*)d_in[6];
  const __nv_bfloat16* gw = (const __nv_bfloat16*)d_in[7];

  void* fp = nullptr; cudaDriverEntryPointQueryResult qr;
  cudaGetDriverEntryPoint("cuTensorMapEncodeTiled", &fp, cudaEnableDefault, &qr);
  EncodeFn enc = (EncodeFn)fp;
  void *pFT, *pET, *pDT, *pW;
  cudaGetSymbolAddress(&pDT, g_DT); cudaGetSymbolAddress(&pW, g_work);
  void *pX = ((Work*)pW)->X, *pT = ((Work*)pW)->T;
  cudaGetSymbolAddress(&pFT, g_FT); cudaGetSymbolAddress(&pET, g_ET);

  Maps mp;
  const CUtensorMapSwizzle S128 = CU_TENSOR_MAP_SWIZZLE_128B, S64 = CU_TENSOR_MAP_SWIZZLE_64B;
  { cuuint64_t d[3] = {512, 64, 32}, s[2] = {32768, 1024}; cuuint32_t b[3] = {64, 64, 2}; encode(enc, &mp.x, x, 3, d, s, b, S128); }
  { cuuint64_t d[2] = {512, 512}, s[1] = {1024}; cuuint32_t b[2] = {64, 64}; encode(enc, &mp.ft, pFT, 2, d, s, b, S128); }
  { cuuint64_t d[4] = {128, 32, 2, 129}, s[3] = {256, 8192, 16384}; cuuint32_t b[4] = {128, 1, 2, 8}; encode(enc, &mp.xs, pX, 4, d, s, b, CU_TENSOR_MAP_SWIZZLE_NONE); }
  { cuuint64_t d[4] = {64, 32, 8, 64}, s[3] = {65536, 128, 1024}; cuuint32_t b[4] = {32, 32, 2, 1}; encode(enc, &mp.ts, pT, 4, d, s, b, S64); }
  { cuuint64_t d[3] = {512, 32, 16}, s[2] = {1024, 32768}; cuuint32_t b[3] = {64, 16, 4}; encode(enc, &mp.fg, pFT, 3, d, s, b, S128); }
  { cuuint64_t d[3] = {512, 64, 32}, s[2] = {1024, 65536}; cuuint32_t b[3] = {64, 64, 2}; encode(enc, &mp.t, pT, 3, d, s, b, S128); }
  { cuuint64_t d[2] = {64, 4096}, s[1] = {128}; cuuint32_t b[2] = {64, 64}; encode(enc, &mp.e, pET, 2, d, s, b, S128); }
  { cuuint64_t d[2] = {1792, 512}, s[1] = {3584}; cuuint32_t b[2] = {64, 64}, b2[2] = {32, 128};
    encode(enc, &mp.g64, Wg, 2, d, s, b, S128); encode(enc, &mp.u64, Wu, 2, d, s, b, S128);
    encode(enc, &mp.g32, Wg, 2, d, s, b2, S64); encode(enc, &mp.u32, Wu, 2, d, s, b2, S64); }
  { cuuint64_t d[2] = {512, 1792}, s[1] = {1024}; cuuint32_t b[2] = {64, 224}; encode(enc, &mp.d224, Wd, 2, d, s, b, S128); }
  { cuuint64_t d[4] = {264, 32, 8, 8}, s[3] = {32896, 512, 4112}; cuuint32_t b[4] = {48, 32, 1, 1};
    encode(enc, &mp.wr, w_r, 4, d, s, b, CU_TENSOR_MAP_SWIZZLE_NONE); encode(enc, &mp.wi, w_i, 4, d, s, b, CU_TENSOR_MAP_SWIZZLE_NONE); }

  cudaFuncSetAttribute(fused_kernel, cudaFuncAttributeMaxDynamicSharedMemorySize, SMEM_BYTES);
  fused_kernel<<<NCTA, 512, SMEM_BYTES>>>((Work*)pW, (const uint16_t*)pDT, w_r, w_i, gw, x, (__nv_bfloat16*)d_out, mp);
}
```

```cpp
#include <cuda_runtime.h>
#include <cuda_bf16.h>
#include <cuda.h>
#include <stdint.h>

namespace tbl {
constexpr double PI = 3.14159265358979323846264338327950288;
constexpr double sin_s(double x) { double t = x, s = x; for (int n = 1; n < 12; n++) { t *= -x * x / ((2 * n) * (2 * n + 1)); s += t; } return s; }
constexpr double cos_s(double x) { double t = 1, s = 1; for (int n = 1; n < 12; n++) { t *= -x * x / ((2 * n - 1) * (2 * n)); s += t; } return s; }
constexpr double cos2048(int m) {
  m &= 2047; if (m > 1024) m = 2048 - m;
  bool neg = false; if (m > 512) { m = 1024 - m; neg = true; }
  double v = (m <= 256) ? cos_s(2 * PI * m / 2048) : sin_s(2 * PI * (512 - m) / 2048);
  return neg ? -v : v;
}
constexpr uint16_t to_bf16(double v) {
  if (v == 0) return 0;
  uint16_t s = 0; if (v < 0) { s = 0x8000; v = -v; }
  int e = 0; while (v >= 2) { v /= 2; e++; } while (v < 1) { v *= 2; e--; }
  double m = (v - 1) * 128; int mi = (int)m; double fr = m - mi;
  if (fr > 0.5 || (fr == 0.5 && (mi & 1))) mi++;
  if (mi == 128) { mi = 0; e++; }
  return (uint16_t)(s | ((e + 127) << 7) | mi);
}
struct CosT { uint16_t v[2048]; constexpr CosT() : v() { for (int i = 0; i < 2048; i++) v[i] = to_bf16(cos2048(i)); } };
struct alignas(1024) FT {
  uint16_t v[512 * 512];
  constexpr FT() : v() {
    CosT c;
    for (int r = 0; r < 512; r++) {
      int k = (r >> 5) * 16 + 2 * (r & 7) + ((r >> 4) & 1), e = (r >> 3) & 1;
      int mul = 4 * k, add = e ? 512 : 0;
      if (k == 0 && e == 1) { mul = 1024; add = 0; }
      for (int d = 0; d < 512; d++) v[r * 512 + d] = c.v[(d * mul + add) & 2047];
    }
  }
};
struct alignas(1024) ET {
  uint16_t v[2048 * 128];
  constexpr ET() : v() {
    CosT c;
    for (int s = 0; s < 2048; s++)
      for (int j = 0; j < 64; j++) {
        const int o = (s & 31) * 8192 + (s >> 5) * 64 + j;
        v[o] = c.v[(s * j) & 2047]; v[o + 4096] = c.v[(s * j + 512) & 2047];
      }
  }
};
struct alignas(1024) DT {
  uint16_t v[64 * 64];
  constexpr DT() : v() {
    CosT c;
    for (int r = 0; r < 64; r++)
      for (int n = 0; n < 64; n++) {
        const int sg = r >> 1, s0 = (sg & ~6) | ((sg & 2) << 1) | ((sg & 4) >> 1), e = r & 1, f = n & 1;
        const int m = 64 * s0 * (n >> 1) + (e == f ? 0 : e ? -512 : 512);
        v[r * 64 + (((n >> 3) ^ (r & 7)) << 3) + (n & 7)] = c.v[m & 2047];
      }
  }
};
}

__device__ constexpr tbl::FT g_FT = tbl::FT();
__device__ constexpr tbl::ET g_ET = tbl::ET();
__device__ constexpr tbl::DT g_DT = tbl::DT();

struct alignas(1024) Work {
  unsigned epoch[132 * 8];
  unsigned cntX[8 * 32], cntT[8 * 32], cntP[128 * 32], cntW[32], cntH[32];
  alignas(16) float gate[16 * 128];
  alignas(16) uint2 Wh[2 * 2048];
  alignas(16) uint2 Ts[32 * 64];
  alignas(1024) uint16_t X[129 * 8192];
  alignas(1024) uint16_t T[32 * 64 * 512];
  alignas(1024) uint4 part[128 * 3 * 1024];
};
__device__ Work g_work;
#define PROF_EV(i) do {} while (0)
#define PROF_CK(i) do {} while (0)

__device__ __forceinline__ uint32_t smem_u32(const void* p) { return (uint32_t)__cvta_generic_to_shared(p); }
__device__ __forceinline__ void mbar_init(uint32_t bar, uint32_t cnt) { asm volatile("mbarrier.init.shared::cta.b64 [%0], %1;" ::"r"(bar), "r"(cnt)); }
__device__ __forceinline__ void mbar_expect_tx(uint32_t bar, uint32_t bytes) { asm volatile("mbarrier.arrive.expect_tx.shared::cta.b64 _, [%0], %1;" ::"r"(bar), "r"(bytes) : "memory"); }
__device__ __forceinline__ void mbar_arrive(uint32_t bar) { asm volatile("mbarrier.arrive.shared::cta.b64 _, [%0];" ::"r"(bar) : "memory"); }
__device__ __forceinline__ bool elect_one() {
  uint32_t p;
  asm volatile("{\n.reg .pred p;\nelect.sync _|p, 0xffffffff;\nselp.u32 %0, 1, 0, p;\n}" : "=r"(p));
  return p;
}
__device__ __forceinline__ void mbar_arrive_if(bool p, uint32_t bar) {
  asm volatile("{\n.reg .pred p;\nsetp.ne.b32 p, %1, 0;\n@p mbarrier.arrive.shared::cta.b64 _, [%0];\n}" ::"r"(bar), "r"((int)p) : "memory");
}
__device__ __forceinline__ void hint_add_if(bool p, unsigned* a) {
  asm volatile("{\n.reg .pred p;\nsetp.ne.b32 p, %1, 0;\n@p red.relaxed.gpu.global.add.u32 [%0], 1;\n}" ::"l"(a), "r"((int)p) : "memory");
}
__device__ __forceinline__ bool mbar_try(uint32_t bar, uint32_t parity) {
  uint32_t ok;
  asm volatile("{\n.reg .pred p;\nmbarrier.test_wait.parity.shared::cta.b64 p, [%1], %2;\nselp.u32 %0, 1, 0, p;\n}" : "=r"(ok) : "r"(bar), "r"(parity) : "memory");
  return ok;
}
__device__ __forceinline__ void mbar_wait(uint32_t bar, uint32_t parity) {
  asm volatile(
      "{\n.reg .pred p;\n.reg .u32 n;\nmov.u32 n, 0;\n"
      "W_LOOP:\nmbarrier.try_wait.parity.shared::cta.b64 p, [%0], %1;\n@p bra W_DONE;\n"
      "add.u32 n, n, 1;\nsetp.lt.u32 p, n, 0x40000;\n@p bra W_LOOP;\ntrap;\nW_DONE:\n}" ::"r"(bar), "r"(parity) : "memory");
}
__device__ __forceinline__ void bulk_load(uint32_t dst, const void* src, uint32_t bytes, uint32_t bar) {
  asm volatile("cp.async.bulk.shared::cluster.global.mbarrier::complete_tx::bytes [%0], [%1], %2, [%3];" ::"r"(dst), "l"(src), "r"(bytes), "r"(bar) : "memory");
}
__device__ __forceinline__ void spin_guard(uint32_t t0) { if ((uint32_t)clock() - t0 > (1u << 30)) __trap(); }
__device__ __forceinline__ float2 ld_x2(const float2* p) { float2 v; asm volatile("ld.relaxed.gpu.global.v2.f32 {%0,%1}, [%2];" : "=f"(v.x), "=f"(v.y) : "l"(p) : "memory"); return v; }
__device__ __forceinline__ void st_u2(uint2* p, uint32_t a, uint32_t b) { asm volatile("st.relaxed.gpu.global.v2.u32 [%0], {%1,%2};" ::"l"(p), "r"(a), "r"(b) : "memory"); }
__device__ __forceinline__ uint32_t ld_x1(const void* p) { uint32_t v; asm volatile("ld.relaxed.gpu.global.u32 %0, [%1];" : "=r"(v) : "l"(p) : "memory"); return v; }
__device__ __forceinline__ uint4 ld_x4(const void* p) { uint4 v; asm volatile("ld.relaxed.gpu.global.v4.u32 {%0,%1,%2,%3}, [%4];" : "=r"(v.x), "=r"(v.y), "=r"(v.z), "=r"(v.w) : "l"(p) : "memory"); return v; }
__device__ __forceinline__ uint32_t mapa(uint32_t a, uint32_t cta) { uint32_t r; asm volatile("mapa.shared::cluster.u32 %0, %1, %2;" : "=r"(r) : "r"(a), "r"(cta)); return r; }
__device__ __forceinline__ void stsm4t(uint32_t a, uint32_t r0, uint32_t r1, uint32_t r2, uint32_t r3) {
  asm volatile("stmatrix.sync.aligned.m8n8.x4.trans.shared.b16 [%0], {%1,%2,%3,%4};" ::"r"(a), "r"(r0), "r"(r1), "r"(r2), "r"(r3) : "memory");
}
__device__ __forceinline__ void hint_add(unsigned* p) { asm volatile("red.relaxed.gpu.global.add.u32 [%0], 1;" ::"l"(p) : "memory"); }
__device__ __forceinline__ void hint_wait(const unsigned* p, unsigned target) {
  const uint32_t t0 = (uint32_t)clock();
  while ((int)(ld_x1(p) - target) < 0) spin_guard(t0);
}
__device__ __forceinline__ void bulk_done_signal(unsigned* p) {
  asm volatile("cp.async.bulk.commit_group;\ncp.async.bulk.wait_group 0;\nfence.proxy.async.global;" ::: "memory");
  hint_add(p);
}
__device__ __forceinline__ void flag_wait(const unsigned* p, unsigned target) {
  hint_wait(p, target);
  asm volatile("fence.proxy.async.global;" ::: "memory");
}
__device__ __forceinline__ void tma2d(uint32_t dst, const CUtensorMap* m, uint32_t bar, int c0, int c1) {
  asm volatile("cp.async.bulk.tensor.2d.shared::cluster.global.mbarrier::complete_tx::bytes [%0], [%1, {%3, %4}], [%2];" ::"r"(dst), "l"(m), "r"(bar), "r"(c0), "r"(c1) : "memory");
}
__device__ __forceinline__ void tma3d(uint32_t dst, const CUtensorMap* m, uint32_t bar, int c0, int c1, int c2) {
  asm volatile("cp.async.bulk.tensor.3d.shared::cluster.global.mbarrier::complete_tx::bytes [%0], [%1, {%3, %4, %5}], [%2];" ::"r"(dst), "l"(m), "r"(bar), "r"(c0), "r"(c1), "r"(c2) : "memory");
}
__device__ __forceinline__ void tma4d(uint32_t dst, const CUtensorMap* m, uint32_t bar, int c0, int c1, int c2, int c3) {
  asm volatile("cp.async.bulk.tensor.4d.shared::cluster.global.mbarrier::complete_tx::bytes [%0], [%1, {%3, %4, %5, %6}], [%2];" ::"r"(dst), "l"(m), "r"(bar), "r"(c0), "r"(c1), "r"(c2), "r"(c3) : "memory");
}
__device__ __forceinline__ void wg_fence() { asm volatile("wgmma.fence.sync.aligned;" ::: "memory"); }
__device__ __forceinline__ void wg_commit() { asm volatile("wgmma.commit_group.sync.aligned;" ::: "memory"); }
template <int N> __device__ __forceinline__ void wg_wait() { asm volatile("wgmma.wait_group.sync.aligned %0;" ::"n"(N) : "memory"); }
template <int O, int N, int NN> __device__ __forceinline__ void fence_regs(float (&d)[NN]) {
#pragma unroll
  for (int i = 0; i < N; i++) asm volatile("" : "+f"(d[O + i])::"memory");
}
__device__ __forceinline__ uint32_t pack_bf16(float lo, float hi) {
  uint32_t r; asm("cvt.rn.bf16x2.f32 %0, %1, %2;" : "=r"(r) : "f"(hi), "f"(lo)); return r;
}
__device__ __forceinline__ uint32_t pack_pin(float lo, float hi) {
  uint32_t r; asm volatile("cvt.rn.bf16x2.f32 %0, %1, %2;" : "=r"(r) : "f"(hi), "f"(lo) : "memory"); return r;
}
__device__ __forceinline__ uint32_t add_bf2(uint32_t a, uint32_t b) { uint32_t r; asm("add.rn.bf16x2 %0, %1, %2;" : "=r"(r) : "r"(a), "r"(b)); return r; }
__device__ __forceinline__ float bf_lo(uint32_t u) { return __uint_as_float(u << 16); }
__device__ __forceinline__ float bf_hi(uint32_t u) { return __uint_as_float(u & 0xffff0000u); }

__device__ __forceinline__ uint64_t d128(uint32_t lo) { uint64_t d; asm("mov.b64 %0, {%1, 0x40000040};" : "=l"(d) : "r"(lo)); return d; }
__device__ __forceinline__ uint64_t d64(uint32_t lo) { uint64_t d; asm("mov.b64 %0, {%1, 0x80000020};" : "=l"(d) : "r"(lo)); return d; }
template<int O,int TB,int ACC,int NN> __device__ __forceinline__ void mma_ss64(float (&d)[NN], uint64_t da, uint64_t db, int sd = 0){
  if constexpr (ACC == 1) asm volatile("wgmma.mma_async.sync.aligned.m64n64k16.f32.bf16.bf16 {%0,%1,%2,%3,%4,%5,%6,%7,%8,%9,%10,%11,%12,%13,%14,%15,%16,%17,%18,%19,%20,%21,%22,%23,%24,%25,%26,%27,%28,%29,%30,%31}, %32, %33, 1, 1, 1, %35, %34;"
   : "+f"(d[O+0]), "+f"(d[O+1]), "+f"(d[O+2]), "+f"(d[O+3]), "+f"(d[O+4]), "+f"(d[O+5]), "+f"(d[O+6]), "+f"(d[O+7]), "+f"(d[O+8]), "+f"(d[O+9]), "+f"(d[O+10]), "+f"(d[O+11]), "+f"(d[O+12]), "+f"(d[O+13]), "+f"(d[O+14]), "+f"(d[O+15]), "+f"(d[O+16]), "+f"(d[O+17]), "+f"(d[O+18]), "+f"(d[O+19]), "+f"(d[O+20]), "+f"(d[O+21]), "+f"(d[O+22]), "+f"(d[O+23]), "+f"(d[O+24]), "+f"(d[O+25]), "+f"(d[O+26]), "+f"(d[O+27]), "+f"(d[O+28]), "+f"(d[O+29]), "+f"(d[O+30]), "+f"(d[O+31])
   : "l"(da), "l"(db), "n"(TB & 1), "n"(TB >> 1));
  else if constexpr (ACC == 0) asm volatile("wgmma.mma_async.sync.aligned.m64n64k16.f32.bf16.bf16 {%0,%1,%2,%3,%4,%5,%6,%7,%8,%9,%10,%11,%12,%13,%14,%15,%16,%17,%18,%19,%20,%21,%22,%23,%24,%25,%26,%27,%28,%29,%30,%31}, %32, %33, 0, 1, 1, %35, %34;"
   : "=f"(d[O+0]), "=f"(d[O+1]), "=f"(d[O+2]), "=f"(d[O+3]), "=f"(d[O+4]), "=f"(d[O+5]), "=f"(d[O+6]), "=f"(d[O+7]), "=f"(d[O+8]), "=f"(d[O+9]), "=f"(d[O+10]), "=f"(d[O+11]), "=f"(d[O+12]), "=f"(d[O+13]), "=f"(d[O+14]), "=f"(d[O+15]), "=f"(d[O+16]), "=f"(d[O+17]), "=f"(d[O+18]), "=f"(d[O+19]), "=f"(d[O+20]), "=f"(d[O+21]), "=f"(d[O+22]), "=f"(d[O+23]), "=f"(d[O+24]), "=f"(d[O+25]), "=f"(d[O+26]), "=f"(d[O+27]), "=f"(d[O+28]), "=f"(d[O+29]), "=f"(d[O+30]), "=f"(d[O+31])
   : "l"(da), "l"(db), "n"(TB & 1), "n"(TB >> 1));
  else asm volatile("{\n.reg .pred p;\nsetp.ne.b32 p, %36, 0;\nwgmma.mma_async.sync.aligned.m64n64k16.f32.bf16.bf16 {%0,%1,%2,%3,%4,%5,%6,%7,%8,%9,%10,%11,%12,%13,%14,%15,%16,%17,%18,%19,%20,%21,%22,%23,%24,%25,%26,%27,%28,%29,%30,%31}, %32, %33, p, 1, 1, %35, %34;\n}"
   : "+f"(d[O+0]), "+f"(d[O+1]), "+f"(d[O+2]), "+f"(d[O+3]), "+f"(d[O+4]), "+f"(d[O+5]), "+f"(d[O+6]), "+f"(d[O+7]), "+f"(d[O+8]), "+f"(d[O+9]), "+f"(d[O+10]), "+f"(d[O+11]), "+f"(d[O+12]), "+f"(d[O+13]), "+f"(d[O+14]), "+f"(d[O+15]), "+f"(d[O+16]), "+f"(d[O+17]), "+f"(d[O+18]), "+f"(d[O+19]), "+f"(d[O+20]), "+f"(d[O+21]), "+f"(d[O+22]), "+f"(d[O+23]), "+f"(d[O+24]), "+f"(d[O+25]), "+f"(d[O+26]), "+f"(d[O+27]), "+f"(d[O+28]), "+f"(d[O+29]), "+f"(d[O+30]), "+f"(d[O+31])
   : "l"(da), "l"(db), "n"(TB & 1), "n"(TB >> 1), "r"(sd));
}
template<int O,int TB,int ACC,int NN> __device__ __forceinline__ void mma_rs64(float (&d)[NN], uint32_t a0, uint32_t a1, uint32_t a2, uint32_t a3, uint64_t db, int sd = 0){
  if constexpr (ACC == 1) asm volatile("wgmma.mma_async.sync.aligned.m64n64k16.f32.bf16.bf16 {%0,%1,%2,%3,%4,%5,%6,%7,%8,%9,%10,%11,%12,%13,%14,%15,%16,%17,%18,%19,%20,%21,%22,%23,%24,%25,%26,%27,%28,%29,%30,%31}, {%32,%33,%34,%35}, %36, 1, 1, 1, %37;"
   : "+f"(d[O+0]), "+f"(d[O+1]), "+f"(d[O+2]), "+f"(d[O+3]), "+f"(d[O+4]), "+f"(d[O+5]), "+f"(d[O+6]), "+f"(d[O+7]), "+f"(d[O+8]), "+f"(d[O+9]), "+f"(d[O+10]), "+f"(d[O+11]), "+f"(d[O+12]), "+f"(d[O+13]), "+f"(d[O+14]), "+f"(d[O+15]), "+f"(d[O+16]), "+f"(d[O+17]), "+f"(d[O+18]), "+f"(d[O+19]), "+f"(d[O+20]), "+f"(d[O+21]), "+f"(d[O+22]), "+f"(d[O+23]), "+f"(d[O+24]), "+f"(d[O+25]), "+f"(d[O+26]), "+f"(d[O+27]), "+f"(d[O+28]), "+f"(d[O+29]), "+f"(d[O+30]), "+f"(d[O+31])
   : "r"(a0), "r"(a1), "r"(a2), "r"(a3), "l"(db), "n"(TB));
  else if constexpr (ACC == 0) asm volatile("wgmma.mma_async.sync.aligned.m64n64k16.f32.bf16.bf16 {%0,%1,%2,%3,%4,%5,%6,%7,%8,%9,%10,%11,%12,%13,%14,%15,%16,%17,%18,%19,%20,%21,%22,%23,%24,%25,%26,%27,%28,%29,%30,%31}, {%32,%33,%34,%35}, %36, 0, 1, 1, %37;"
   : "=f"(d[O+0]), "=f"(d[O+1]), "=f"(d[O+2]), "=f"(d[O+3]), "=f"(d[O+4]), "=f"(d[O+5]), "=f"(d[O+6]), "=f"(d[O+7]), "=f"(d[O+8]), "=f"(d[O+9]), "=f"(d[O+10]), "=f"(d[O+11]), "=f"(d[O+12]), "=f"(d[O+13]), "=f"(d[O+14]), "=f"(d[O+15]), "=f"(d[O+16]), "=f"(d[O+17]), "=f"(d[O+18]), "=f"(d[O+19]), "=f"(d[O+20]), "=f"(d[O+21]), "=f"(d[O+22]), "=f"(d[O+23]), "=f"(d[O+24]), "=f"(d[O+25]), "=f"(d[O+26]), "=f"(d[O+27]), "=f"(d[O+28]), "=f"(d[O+29]), "=f"(d[O+30]), "=f"(d[O+31])
   : "r"(a0), "r"(a1), "r"(a2), "r"(a3), "l"(db), "n"(TB));
  else asm volatile("{\n.reg .pred p;\nsetp.ne.b32 p, %38, 0;\nwgmma.mma_async.sync.aligned.m64n64k16.f32.bf16.bf16 {%0,%1,%2,%3,%4,%5,%6,%7,%8,%9,%10,%11,%12,%13,%14,%15,%16,%17,%18,%19,%20,%21,%22,%23,%24,%25,%26,%27,%28,%29,%30,%31}, {%32,%33,%34,%35}, %36, p, 1, 1, %37;\n}"
   : "+f"(d[O+0]), "+f"(d[O+1]), "+f"(d[O+2]), "+f"(d[O+3]), "+f"(d[O+4]), "+f"(d[O+5]), "+f"(d[O+6]), "+f"(d[O+7]), "+f"(d[O+8]), "+f"(d[O+9]), "+f"(d[O+10]), "+f"(d[O+11]), "+f"(d[O+12]), "+f"(d[O+13]), "+f"(d[O+14]), "+f"(d[O+15]), "+f"(d[O+16]), "+f"(d[O+17]), "+f"(d[O+18]), "+f"(d[O+19]), "+f"(d[O+20]), "+f"(d[O+21]), "+f"(d[O+22]), "+f"(d[O+23]), "+f"(d[O+24]), "+f"(d[O+25]), "+f"(d[O+26]), "+f"(d[O+27]), "+f"(d[O+28]), "+f"(d[O+29]), "+f"(d[O+30]), "+f"(d[O+31])
   : "r"(a0), "r"(a1), "r"(a2), "r"(a3), "l"(db), "n"(TB), "r"(sd));
}
template<int O,int TB,int ACC,int NN> __device__ __forceinline__ void mma_ss128(float (&d)[NN], uint64_t da, uint64_t db, int sd = 0){
  if constexpr (ACC == 1) asm volatile("wgmma.mma_async.sync.aligned.m64n128k16.f32.bf16.bf16 {%0,%1,%2,%3,%4,%5,%6,%7,%8,%9,%10,%11,%12,%13,%14,%15,%16,%17,%18,%19,%20,%21,%22,%23,%24,%25,%26,%27,%28,%29,%30,%31,%32,%33,%34,%35,%36,%37,%38,%39,%40,%41,%42,%43,%44,%45,%46,%47,%48,%49,%50,%51,%52,%53,%54,%55,%56,%57,%58,%59,%60,%61,%62,%63}, %64, %65, 1, 1, 1, %67, %66;"
   : "+f"(d[O+0]), "+f"(d[O+1]), "+f"(d[O+2]), "+f"(d[O+3]), "+f"(d[O+4]), "+f"(d[O+5]), "+f"(d[O+6]), "+f"(d[O+7]), "+f"(d[O+8]), "+f"(d[O+9]), "+f"(d[O+10]), "+f"(d[O+11]), "+f"(d[O+12]), "+f"(d[O+13]), "+f"(d[O+14]), "+f"(d[O+15]), "+f"(d[O+16]), "+f"(d[O+17]), "+f"(d[O+18]), "+f"(d[O+19]), "+f"(d[O+20]), "+f"(d[O+21]), "+f"(d[O+22]), "+f"(d[O+23]), "+f"(d[O+24]), "+f"(d[O+25]), "+f"(d[O+26]), "+f"(d[O+27]), "+f"(d[O+28]), "+f"(d[O+29]), "+f"(d[O+30]), "+f"(d[O+31]), "+f"(d[O+32]), "+f"(d[O+33]), "+f"(d[O+34]), "+f"(d[O+35]), "+f"(d[O+36]), "+f"(d[O+37]), "+f"(d[O+38]), "+f"(d[O+39]), "+f"(d[O+40]), "+f"(d[O+41]), "+f"(d[O+42]), "+f"(d[O+43]), "+f"(d[O+44]), "+f"(d[O+45]), "+f"(d[O+46]), "+f"(d[O+47]), "+f"(d[O+48]), "+f"(d[O+49]), "+f"(d[O+50]), "+f"(d[O+51]), "+f"(d[O+52]), "+f"(d[O+53]), "+f"(d[O+54]), "+f"(d[O+55]), "+f"(d[O+56]), "+f"(d[O+57]), "+f"(d[O+58]), "+f"(d[O+59]), "+f"(d[O+60]), "+f"(d[O+61]), "+f"(d[O+62]), "+f"(d[O+63])
   : "l"(da), "l"(db), "n"(TB & 1), "n"(TB >> 1));
  else if constexpr (ACC == 0) asm volatile("wgmma.mma_async.sync.aligned.m64n128k16.f32.bf16.bf16 {%0,%1,%2,%3,%4,%5,%6,%7,%8,%9,%10,%11,%12,%13,%14,%15,%16,%17,%18,%19,%20,%21,%22,%23,%24,%25,%26,%27,%28,%29,%30,%31,%32,%33,%34,%35,%36,%37,%38,%39,%40,%41,%42,%43,%44,%45,%46,%47,%48,%49,%50,%51,%52,%53,%54,%55,%56,%57,%58,%59,%60,%61,%62,%63}, %64, %65, 0, 1, 1, %67, %66;"
   : "=f"(d[O+0]), "=f"(d[O+1]), "=f"(d[O+2]), "=f"(d[O+3]), "=f"(d[O+4]), "=f"(d[O+5]), "=f"(d[O+6]), "=f"(d[O+7]), "=f"(d[O+8]), "=f"(d[O+9]), "=f"(d[O+10]), "=f"(d[O+11]), "=f"(d[O+12]), "=f"(d[O+13]), "=f"(d[O+14]), "=f"(d[O+15]), "=f"(d[O+16]), "=f"(d[O+17]), "=f"(d[O+18]), "=f"(d[O+19]), "=f"(d[O+20]), "=f"(d[O+21]), "=f"(d[O+22]), "=f"(d[O+23]), "=f"(d[O+24]), "=f"(d[O+25]), "=f"(d[O+26]), "=f"(d[O+27]), "=f"(d[O+28]), "=f"(d[O+29]), "=f"(d[O+30]), "=f"(d[O+31]), "=f"(d[O+32]), "=f"(d[O+33]), "=f"(d[O+34]), "=f"(d[O+35]), "=f"(d[O+36]), "=f"(d[O+37]), "=f"(d[O+38]), "=f"(d[O+39]), "=f"(d[O+40]), "=f"(d[O+41]), "=f"(d[O+42]), "=f"(d[O+43]), "=f"(d[O+44]), "=f"(d[O+45]), "=f"(d[O+46]), "=f"(d[O+47]), "=f"(d[O+48]), "=f"(d[O+49]), "=f"(d[O+50]), "=f"(d[O+51]), "=f"(d[O+52]), "=f"(d[O+53]), "=f"(d[O+54]), "=f"(d[O+55]), "=f"(d[O+56]), "=f"(d[O+57]), "=f"(d[O+58]), "=f"(d[O+59]), "=f"(d[O+60]), "=f"(d[O+61]), "=f"(d[O+62]), "=f"(d[O+63])
   : "l"(da), "l"(db), "n"(TB & 1), "n"(TB >> 1));
  else asm volatile("{\n.reg .pred p;\nsetp.ne.b32 p, %68, 0;\nwgmma.mma_async.sync.aligned.m64n128k16.f32.bf16.bf16 {%0,%1,%2,%3,%4,%5,%6,%7,%8,%9,%10,%11,%12,%13,%14,%15,%16,%17,%18,%19,%20,%21,%22,%23,%24,%25,%26,%27,%28,%29,%30,%31,%32,%33,%34,%35,%36,%37,%38,%39,%40,%41,%42,%43,%44,%45,%46,%47,%48,%49,%50,%51,%52,%53,%54,%55,%56,%57,%58,%59,%60,%61,%62,%63}, %64, %65, p, 1, 1, %67, %66;\n}"
   : "+f"(d[O+0]), "+f"(d[O+1]), "+f"(d[O+2]), "+f"(d[O+3]), "+f"(d[O+4]), "+f"(d[O+5]), "+f"(d[O+6]), "+f"(d[O+7]), "+f"(d[O+8]), "+f"(d[O+9]), "+f"(d[O+10]), "+f"(d[O+11]), "+f"(d[O+12]), "+f"(d[O+13]), "+f"(d[O+14]), "+f"(d[O+15]), "+f"(d[O+16]), "+f"(d[O+17]), "+f"(d[O+18]), "+f"(d[O+19]), "+f"(d[O+20]), "+f"(d[O+21]), "+f"(d[O+22]), "+f"(d[O+23]), "+f"(d[O+24]), "+f"(d[O+25]), "+f"(d[O+26]), "+f"(d[O+27]), "+f"(d[O+28]), "+f"(d[O+29]), "+f"(d[O+30]), "+f"(d[O+31]), "+f"(d[O+32]), "+f"(d[O+33]), "+f"(d[O+34]), "+f"(d[O+35]), "+f"(d[O+36]), "+f"(d[O+37]), "+f"(d[O+38]), "+f"(d[O+39]), "+f"(d[O+40]), "+f"(d[O+41]), "+f"(d[O+42]), "+f"(d[O+43]), "+f"(d[O+44]), "+f"(d[O+45]), "+f"(d[O+46]), "+f"(d[O+47]), "+f"(d[O+48]), "+f"(d[O+49]), "+f"(d[O+50]), "+f"(d[O+51]), "+f"(d[O+52]), "+f"(d[O+53]), "+f"(d[O+54]), "+f"(d[O+55]), "+f"(d[O+56]), "+f"(d[O+57]), "+f"(d[O+58]), "+f"(d[O+59]), "+f"(d[O+60]), "+f"(d[O+61]), "+f"(d[O+62]), "+f"(d[O+63])
   : "l"(da), "l"(db), "n"(TB & 1), "n"(TB >> 1), "r"(sd));
}
template<int O,int TB,int ACC,int NN> __device__ __forceinline__ void mma_rs128(float (&d)[NN], uint32_t a0, uint32_t a1, uint32_t a2, uint32_t a3, uint64_t db, int sd = 0){
  if constexpr (ACC == 1) asm volatile("wgmma.mma_async.sync.aligned.m64n128k16.f32.bf16.bf16 {%0,%1,%2,%3,%4,%5,%6,%7,%8,%9,%10,%11,%12,%13,%14,%15,%16,%17,%18,%19,%20,%21,%22,%23,%24,%25,%26,%27,%28,%29,%30,%31,%32,%33,%34,%35,%36,%37,%38,%39,%40,%41,%42,%43,%44,%45,%46,%47,%48,%49,%50,%51,%52,%53,%54,%55,%56,%57,%58,%59,%60,%61,%62,%63}, {%64,%65,%66,%67}, %68, 1, 1, 1, %69;"
   : "+f"(d[O+0]), "+f"(d[O+1]), "+f"(d[O+2]), "+f"(d[O+3]), "+f"(d[O+4]), "+f"(d[O+5]), "+f"(d[O+6]), "+f"(d[O+7]), "+f"(d[O+8]), "+f"(d[O+9]), "+f"(d[O+10]), "+f"(d[O+11]), "+f"(d[O+12]), "+f"(d[O+13]), "+f"(d[O+14]), "+f"(d[O+15]), "+f"(d[O+16]), "+f"(d[O+17]), "+f"(d[O+18]), "+f"(d[O+19]), "+f"(d[O+20]), "+f"(d[O+21]), "+f"(d[O+22]), "+f"(d[O+23]), "+f"(d[O+24]), "+f"(d[O+25]), "+f"(d[O+26]), "+f"(d[O+27]), "+f"(d[O+28]), "+f"(d[O+29]), "+f"(d[O+30]), "+f"(d[O+31]), "+f"(d[O+32]), "+f"(d[O+33]), "+f"(d[O+34]), "+f"(d[O+35]), "+f"(d[O+36]), "+f"(d[O+37]), "+f"(d[O+38]), "+f"(d[O+39]), "+f"(d[O+40]), "+f"(d[O+41]), "+f"(d[O+42]), "+f"(d[O+43]), "+f"(d[O+44]), "+f"(d[O+45]), "+f"(d[O+46]), "+f"(d[O+47]), "+f"(d[O+48]), "+f"(d[O+49]), "+f"(d[O+50]), "+f"(d[O+51]), "+f"(d[O+52]), "+f"(d[O+53]), "+f"(d[O+54]), "+f"(d[O+55]), "+f"(d[O+56]), "+f"(d[O+57]), "+f"(d[O+58]), "+f"(d[O+59]), "+f"(d[O+60]), "+f"(d[O+61]), "+f"(d[O+62]), "+f"(d[O+63])
   : "r"(a0), "r"(a1), "r"(a2), "r"(a3), "l"(db), "n"(TB));
  else if constexpr (ACC == 0) asm volatile("wgmma.mma_async.sync.aligned.m64n128k16.f32.bf16.bf16 {%0,%1,%2,%3,%4,%5,%6,%7,%8,%9,%10,%11,%12,%13,%14,%15,%16,%17,%18,%19,%20,%21,%22,%23,%24,%25,%26,%27,%28,%29,%30,%31,%32,%33,%34,%35,%36,%37,%38,%39,%40,%41,%42,%43,%44,%45,%46,%47,%48,%49,%50,%51,%52,%53,%54,%55,%56,%57,%58,%59,%60,%61,%62,%63}, {%64,%65,%66,%67}, %68, 0, 1, 1, %69;"
   : "=f"(d[O+0]), "=f"(d[O+1]), "=f"(d[O+2]), "=f"(d[O+3]), "=f"(d[O+4]), "=f"(d[O+5]), "=f"(d[O+6]), "=f"(d[O+7]), "=f"(d[O+8]), "=f"(d[O+9]), "=f"(d[O+10]), "=f"(d[O+11]), "=f"(d[O+12]), "=f"(d[O+13]), "=f"(d[O+14]), "=f"(d[O+15]), "=f"(d[O+16]), "=f"(d[O+17]), "=f"(d[O+18]), "=f"(d[O+19]), "=f"(d[O+20]), "=f"(d[O+21]), "=f"(d[O+22]), "=f"(d[O+23]), "=f"(d[O+24]), "=f"(d[O+25]), "=f"(d[O+26]), "=f"(d[O+27]), "=f"(d[O+28]), "=f"(d[O+29]), "=f"(d[O+30]), "=f"(d[O+31]), "=f"(d[O+32]), "=f"(d[O+33]), "=f"(d[O+34]), "=f"(d[O+35]), "=f"(d[O+36]), "=f"(d[O+37]), "=f"(d[O+38]), "=f"(d[O+39]), "=f"(d[O+40]), "=f"(d[O+41]), "=f"(d[O+42]), "=f"(d[O+43]), "=f"(d[O+44]), "=f"(d[O+45]), "=f"(d[O+46]), "=f"(d[O+47]), "=f"(d[O+48]), "=f"(d[O+49]), "=f"(d[O+50]), "=f"(d[O+51]), "=f"(d[O+52]), "=f"(d[O+53]), "=f"(d[O+54]), "=f"(d[O+55]), "=f"(d[O+56]), "=f"(d[O+57]), "=f"(d[O+58]), "=f"(d[O+59]), "=f"(d[O+60]), "=f"(d[O+61]), "=f"(d[O+62]), "=f"(d[O+63])
   : "r"(a0), "r"(a1), "r"(a2), "r"(a3), "l"(db), "n"(TB));
  else asm volatile("{\n.reg .pred p;\nsetp.ne.b32 p, %70, 0;\nwgmma.mma_async.sync.aligned.m64n128k16.f32.bf16.bf16 {%0,%1,%2,%3,%4,%5,%6,%7,%8,%9,%10,%11,%12,%13,%14,%15,%16,%17,%18,%19,%20,%21,%22,%23,%24,%25,%26,%27,%28,%29,%30,%31,%32,%33,%34,%35,%36,%37,%38,%39,%40,%41,%42,%43,%44,%45,%46,%47,%48,%49,%50,%51,%52,%53,%54,%55,%56,%57,%58,%59,%60,%61,%62,%63}, {%64,%65,%66,%67}, %68, p, 1, 1, %69;\n}"
   : "+f"(d[O+0]), "+f"(d[O+1]), "+f"(d[O+2]), "+f"(d[O+3]), "+f"(d[O+4]), "+f"(d[O+5]), "+f"(d[O+6]), "+f"(d[O+7]), "+f"(d[O+8]), "+f"(d[O+9]), "+f"(d[O+10]), "+f"(d[O+11]), "+f"(d[O+12]), "+f"(d[O+13]), "+f"(d[O+14]), "+f"(d[O+15]), "+f"(d[O+16]), "+f"(d[O+17]), "+f"(d[O+18]), "+f"(d[O+19]), "+f"(d[O+20]), "+f"(d[O+21]), "+f"(d[O+22]), "+f"(d[O+23]), "+f"(d[O+24]), "+f"(d[O+25]), "+f"(d[O+26]), "+f"(d[O+27]), "+f"(d[O+28]), "+f"(d[O+29]), "+f"(d[O+30]), "+f"(d[O+31]), "+f"(d[O+32]), "+f"(d[O+33]), "+f"(d[O+34]), "+f"(d[O+35]), "+f"(d[O+36]), "+f"(d[O+37]), "+f"(d[O+38]), "+f"(d[O+39]), "+f"(d[O+40]), "+f"(d[O+41]), "+f"(d[O+42]), "+f"(d[O+43]), "+f"(d[O+44]), "+f"(d[O+45]), "+f"(d[O+46]), "+f"(d[O+47]), "+f"(d[O+48]), "+f"(d[O+49]), "+f"(d[O+50]), "+f"(d[O+51]), "+f"(d[O+52]), "+f"(d[O+53]), "+f"(d[O+54]), "+f"(d[O+55]), "+f"(d[O+56]), "+f"(d[O+57]), "+f"(d[O+58]), "+f"(d[O+59]), "+f"(d[O+60]), "+f"(d[O+61]), "+f"(d[O+62]), "+f"(d[O+63])
   : "r"(a0), "r"(a1), "r"(a2), "r"(a3), "l"(db), "n"(TB), "r"(sd));
}

#define NEARLY 0
#define XAHEAD 3
#define HEADN 6
#define WBATCH 1
#define WB 8
#define WSLEEP 20
#define XSPREAD 4
#define NOSEND 0
#define MSPLIT 2
#define PFALL 1
#define L2PF 0
#define STAG 0
#define EPF 2
#define XNB 2
#define FNB 0
#define GNB 0
#define TH 4
#define PF0 4
#define FSPLIT 1
#define MGLU 1
#define SPC 2
#define TL 14
#define GKB 4
#define T0A 7
#define T0B 11
#define TGATE 1
#define ZLATE 0
#define EARLYADD 0
#define OA 3
#define OB 11
#define EB 8
#define SPACE 100
#define WPF 1
#define WAFTER 7
#define WPACE 0
#define GATE_AT 4
#define TPACE 40
#define PFMODE 0
#define MAPMODE 1
template <int V> struct IC { static constexpr int value = V; };
struct Maps { CUtensorMap x, ft, g64, u64, e, wr, wi, xs, ts, t, g32, u32, d224, fg; };

constexpr int NCTA = 130;
constexpr int U = 16384;
constexpr int TB = 36864;
constexpr int OFF_RING = 8 * U, OFF_Z = 12 * U, OFF_XB = 12 * U, OFF_T = 13 * U, OFF_D = OFF_T;
constexpr int OFF_BAR = 14 * U, OFF_SP = OFF_BAR + 512, OFF_G = OFF_SP + 1024 + 128;
constexpr int SMEM_BYTES = OFF_G + 512;
constexpr int B_FX = 0, B_FA = 8, B_FT = 12, B_Z = 16, B_W = 24, B_HX = 25, B_TL = 26, B_HP = 27, B_WR = 31, B_E0 = 35;
constexpr int B_EA = 36, B_ET = 40, B_PZ = 44, B_RDY = 46, B_FE = 47;
constexpr int B_T = 51, B_XS = 52, B_G = 54, B_RD0 = 55, B_HS = 56, B_AK = 58, B_HH = 60, NBAR = 64;
__host__ __device__ constexpr int rslot(int n) { return n & 3; }
__host__ __device__ constexpr int rpar(int n) { return (n >> 2) & 1; }

__global__ void __cluster_dims__(2, 1, 1) __launch_bounds__(512, 1)
fused_kernel(Work* __restrict__ ws, const uint16_t* __restrict__ dtab, const __nv_bfloat16* __restrict__ w_r, const __nv_bfloat16* __restrict__ w_i,
             const __nv_bfloat16* __restrict__ gate_w, const __nv_bfloat16* __restrict__ x, __nv_bfloat16* __restrict__ out,
             const __grid_constant__ Maps maps) {
  extern __shared__ __align__(1024) uint8_t smem[];
  if (threadIdx.x < 32 && elect_one()) {
#pragma unroll
    for (int i = 0; i < PF0; i++) asm volatile("prefetch.tensormap [%0];" ::"l"((const char*)&maps + i * 128) : "memory");
  }
  const uint32_t sb = smem_u32(smem);
  const uint32_t bars = sb + OFF_BAR;
  const int tid = threadIdx.x, lane = tid & 31;
  const int warp = __shfl_sync(0xffffffffu, tid >> 5, 0);
  const bool helper = blockIdx.x >= 128;
  const int cl = (blockIdx.x >> 1) & 63, rank = blockIdx.x & 1;
  const int q4 = (cl & 1) | ((cl >> 2) & 2), rb = ((cl >> 1) & 3) | ((cl >> 4) << 2);
  const int j = 2 * q4 + rank;
  const int f_full = 448 * q4 + (rank ? 256 : 0);
  const int f_half = 448 * q4 + (rank ? 224 : 192);

  if (tid == 64) { PROF_EV(0); PROF_CK(40); }
  auto part_load = [&](int i, unsigned ep1) {
    const uint32_t bytes = i < 2 ? U : U / 2;
    mbar_wait(bars + 8 * (B_PZ + (i == 0)), 0);
    mbar_expect_tx(bars + 8 * (B_HP + i), bytes);
    flag_wait(&ws->cntP[32 * (rb * 8 + j) + 8 * i], ep1 * (i < 2 ? 2u : 4u));
    bulk_load(sb + (i == 0 ? OFF_T : i == 1 ? 0 : i * (U / 2)), ws->part + (size_t)(rb * 8 + j) * 3072 + (i < 2 ? i * 1024 : 1024 + i * 512), bytes, bars + 8 * (B_HP + i));
    if (i == 2) PROF_EV(26);
  };
  if (warp < 8) {
    if (!helper && tid < 32) {
      const int r = 16 * j + (tid & 15);
      asm volatile("prefetch.global.L2 [%0];" ::"l"(x + (size_t)(2 * rb + (r >> 6) + 32 * (r & 63)) * 512 + 64 * (tid >> 4)));
    }
    asm volatile("barrier.cluster.arrive.relaxed.aligned;" ::: "memory");
    asm volatile("setmaxnreg.inc.sync.aligned.u32 192;");
    if (!helper) {
      const int wg = warp >> 2, w = warp & 3, g = lane >> 2;
      const bool elect = (tid & 127) == 0;
      float cX[32], cA[64], cB[64], cC[64], ci[64], ct[64];
      const int zero = blockIdx.x >> 16;
      uint32_t h[56], yf[16];
      const uint32_t d0 = (sb & 0x3FFFF) >> 4;
      const uint32_t dK = d0 | (1u << 16), dN = d0 | (512u << 16);
      const uint32_t dX = dK + wg * 512;
      constexpr uint32_t RING = OFF_RING >> 4;
      auto waitA = [&](int n) { mbar_wait(bars + 8 * (B_FA + rslot(n)), rpar(n)); };
      auto freeA = [&](int n) { mbar_arrive_if(elect, bars + 8 * (B_EA + rslot(n))); };
      auto nop = [] {};

      asm volatile("bar.sync 0, 384;" ::: "memory");
#pragma unroll 1
      for (int i = 0; i < 4; i++) {
        const uint64_t dx = d128(dX + i * 2048), df = d128(dK + (OFF_XB >> 4) + (i & 1) * 1024);
        mbar_wait(bars + 8 * (B_FX + 2 * i), 0);
        wg_fence();
        mma_ss64<0, 0, 2>(cX, df, dx, i);
        mma_ss64<0, 0, 1>(cX, df + 2, dx + 2);
        wg_commit(); wg_wait<1>();
        mbar_arrive_if(elect && i, bars + 8 * (B_EA + rslot(i - 1)));
        mma_ss64<0, 0, 1>(cX, df + 4, dx + 4);
        mma_ss64<0, 0, 1>(cX, df + 6, dx + 6);
        if (i == 0 && tid == 0) PROF_EV(1);
        mbar_wait(bars + 8 * (B_FX + 2 * i + 1), 0);
        wg_fence();
#pragma unroll
        for (int k = 0; k < 4; k++) mma_ss64<0, 0, 1>(cX, df + (512 + k * 2), dx + (1024 + k * 2));
        wg_commit();
        waitA(i);
        wg_fence();
        const uint64_t da = d128(dX + i * 1024), db = d128(dN + RING + i * 1024);
        mma_ss128<0, 1, 2>(cA, da, db, i);
        wg_commit(); wg_wait<1>();
        mbar_arrive_if(elect, bars + 8 * (B_FE + i));
#pragma unroll
        for (int k = 1; k < 4; k++) mma_ss128<0, 1, 1>(cA, da + k * 2, db + k * 128);
        wg_commit();
      }
      fence_regs<0, 32>(cX);
#pragma unroll
      for (int e = 0; e < 16; e++) yf[e] = pack_pin(cX[2 * e], cX[2 * e + 1]);
      if (tid == 0) { PROF_EV(2); PROF_CK(42); }
      {
        waitA(4); mbar_wait(bars + 8 * B_E0, 0);
        const uint64_t de = d128(dN + (wg ? RING : OFF_XB >> 4));
        wg_fence();
        mma_rs128<0, 1, 0>(cB, yf[0], yf[1], yf[2], yf[3], de);
        wg_commit();
        wg_wait<1>();
        freeA(3);
#pragma unroll
        for (int k = 1; k < 4; k++) mma_rs128<0, 1, 1>(cB, yf[4 * k], yf[4 * k + 1], yf[4 * k + 2], yf[4 * k + 3], de + k * 128);
        wg_commit();
      }
      bool rel = false;
      auto acquire = [&](int n) {
        rel = elect;
        if (!mbar_try(bars + 8 * (B_FA + rslot(n)), rpar(n))) { wg_wait<0>(); freeA(n - 1); rel = false; waitA(n); }
      };
      auto freeP = [&](int n) { mbar_arrive_if(rel, bars + 8 * (B_EA + rslot(n - 1))); };
      auto ffn_step = [&](auto first, auto split, float (&acc)[64], int n, int kb, auto done, auto work) {
        constexpr int SPLIT = decltype(split)::value;
        acquire(n);
        wg_fence();
        const uint64_t dx = d128(dX + kb * 1024), db = d128(dN + RING + rslot(n) * 1024);
        mma_ss128<0, 1, decltype(first)::value>(acc, dx, db, kb);
#pragma unroll
        for (int k = 1; k < SPLIT; k++) mma_ss128<0, 1, 1>(acc, dx + k * 2, db + k * 128);
        wg_commit();
        work();
        wg_wait<1>();
        freeP(n);
        done();
        if (SPLIT < 4) {
          wg_fence();
#pragma unroll
          for (int k = SPLIT; k < 4; k++) mma_ss128<0, 1, 1>(acc, dx + k * 2, db + k * 128);
          wg_commit();
        }
      };
      {
        const int s0 = 2 * rb + wg, kr = 2 * ((s0 & 1) | ((s0 & 4) >> 1));
        const int m = lane >> 3, r = lane & 7;
        const uint32_t a0 = sb + OFF_XB + wg * 8192 + ((2 * (m >> 1) + (r >> 2)) * 2 + (w & 1)) * 256 + (m & 1) * 128 + (((2 * (r & 3) + ((w >> 1) ^ (r >> 2))) ^ (kr + (m & 1))) << 4);
        ffn_step(IC<1>(), IC<4>(), cA, 5, 4, [&] { fence_regs<0, 64>(cB); }, nop);
        asm volatile("bar.sync 5, 256;" ::: "memory");
        auto stage = [&](int i) {
          stsm4t(a0 + i * 2048, pack_bf16(cB[8 * i] - cB[34 + 8 * i], cB[8 * i + 1] - cB[35 + 8 * i]),
                 pack_bf16(cB[32 + 8 * i] + cB[8 * i + 2], cB[33 + 8 * i] + cB[8 * i + 3]),
                 pack_bf16(cB[8 * i + 4] - cB[38 + 8 * i], cB[8 * i + 5] - cB[39 + 8 * i]),
                 pack_bf16(cB[36 + 8 * i] + cB[8 * i + 6], cB[37 + 8 * i] + cB[8 * i + 7]));
          if (j == 0 && w == 0) {
            const uint32_t a1 = r ? sb + OFF_SP + 1024 : sb + OFF_SP + wg * 512 + (m & 1) * 256 + (m >> 1) * 128;
#pragma unroll
            for (int n = 2 * i; n < 2 * i + 2; n++)
              asm volatile("stmatrix.sync.aligned.m8n8.x4.shared.b16 [%0], {%1,%2,%3,%4};" ::"r"(a1 + ((n ^ (kr + (m >> 1)) ^ r) << 4)),
                           "r"(pack_bf16(cB[4 * n], cB[4 * n + 1])), "r"(pack_bf16(cB[4 * n + 2], cB[4 * n + 3])),
                           "r"(pack_bf16(cB[32 + 4 * n], cB[33 + 4 * n])), "r"(pack_bf16(cB[34 + 4 * n], cB[35 + 4 * n])) : "memory");
          }
        };
        auto publish = [&] {
          asm volatile("fence.proxy.async.shared::cta;" ::: "memory");
          __syncwarp();
          mbar_arrive_if(lane == 0, bars + 8 * (B_XS + wg));
          if (tid == 0) PROF_EV(3);
        };
        stage(0);
        ffn_step(IC<1>(), IC<FSPLIT>(), cA, 6, 5, nop, nop);
        stage(1);
        ffn_step(IC<1>(), IC<FSPLIT>(), cA, 7, 6, nop, nop);
        stage(2);
        ffn_step(IC<1>(), IC<2>(), cA, 8, 7, [&] { stage(3); }, nop);
        publish();
      }
      uint32_t gb0 = 0, gb1 = 0;
      uint32_t ob[2] = {0, 0};
      auto glu = [&](auto& acc, int half, int ho, int i0, int i1) {
#pragma unroll
        for (int i = i0; i < i1; i++)
          asm volatile("{\n.reg .b32 a, b;\ncvt.rn.relu.bf16x2.f32 a, %2, %1;\ncvt.rn.bf16x2.f32 b, %4, %3;\nmul.rn.bf16x2 a, a, b;\nmul.rn.bf16x2 %0, a, %5;\n}"
                       : "=r"(h[ho + i]) : "f"(acc[2 * i]), "f"(acc[2 * i + 1]), "f"(acc[half + 2 * i]), "f"(acc[half + 1 + 2 * i]), "r"(ob[i & 1]) : "memory");
      };
      ffn_step(IC<2>(), IC<1>(), cB, 9, zero, nop, nop);
#pragma unroll 1
      for (int kb = 1; kb < 8; kb++)
        ffn_step(IC<1>(), IC<FSPLIT>(), cB, 9 + kb, kb, nop, [&] {
          if (kb == GKB) {
            mbar_wait(bars + 8 * B_G, 0);
            asm volatile("ld.shared.u32 %0, [%2];\nld.shared.u32 %1, [%2+32];" : "=r"(gb0), "=r"(gb1) : "r"(sb + OFF_G + (wg * 64 + w * 16 + g) * 4) : "memory");
          } else if (kb == 5 + 2 * wg) {
            ob[0] = pack_bf16(1.0f - bf_hi(gb0), 1.0f - bf_hi(gb0)); ob[1] = pack_bf16(1.0f - bf_hi(gb1), 1.0f - bf_hi(gb1));
            glu(cA, 32, 0, 0, 16);
          }
        });
      const uint32_t tag = gb0 & 1;
      const float g0 = bf_hi(gb0), g1 = bf_hi(gb1);
      if (tid == 0) { PROF_EV(4); PROF_CK(43); }
      auto m_step = [&](auto first, int i) {
        acquire(17 + i);
        wg_fence();
        const uint64_t dx = d128(dX + i * 2048), dm = d64(dN + RING + rslot(17 + i) * 1024);
        mma_ss64<0, 1, decltype(first)::value>(ct, dx, dm);
#pragma unroll
        for (int k = 1; k < MSPLIT; k++) mma_ss64<0, 1, 1>(ct, dx + ((k >> 2) * 1024 + (k & 3) * 2), dm + k * 64);
        wg_commit();
        wg_wait<1>();
        freeP(17 + i);
        wg_fence();
#pragma unroll
        for (int k = MSPLIT; k < 8; k++) mma_ss64<0, 1, 1>(ct, dx + ((k >> 2) * 1024 + (k & 3) * 2), dm + k * 64);
        wg_commit();
      };
      m_step(IC<0>(), 0);
#pragma unroll 1
      for (int i = 1; i < 5; i++) {
        if (i == 1 + 2 * wg) glu(cB, 32, 16, 0, 16);
        if (i < 4) m_step(IC<1>(), i);
      }
      if (tid == 0) { PROF_EV(5); PROF_CK(44); }
      ffn_step(IC<0>(), IC<1>(), cC, 21, 0, nop, nop);
#pragma unroll 1
      for (int kb = 1; kb < 8; kb++)
        ffn_step(IC<1>(), IC<FSPLIT>(), cC, 21 + kb, kb, [&] { mbar_arrive_if(elect && !(kb & 1), bars + 8 * (B_ET + (kb >> 1) - 1)); }, [&] {
          if (kb == 1 + wg) glu(ct, 16, 48, 0, 8);
        });

      auto twait = [&](uint32_t bar, uint32_t par, int) { mbar_wait(bar, par); };
      auto tr = [] {};
      const int fo = warp * 128 + lane;
      auto fetch = [&](uint4 (&pv)[4], int z) {
        twait(bars + 8 * (z < 4 ? B_Z + 2 * z + wg : z < 6 ? B_HP + z - 4 : B_HP + 2 + wg), 0, 8 + z);
        const uint8_t* src = smem + (z < 4 ? OFF_Z - z * U : z == 4 ? OFF_T : (z - 5) * U) + fo * 16;
#pragma unroll
        for (int i = 0; i < 4; i++) pv[i] = *(const uint4*)(src + i * 512);
      };
      auto tile_mma = [&](auto off, int t, int k0, int k1, bool fresh = false) {
        constexpr int O = decltype(off)::value;
        const uint64_t db = d128(dN + (t & 3) * (TB >> 4)), dw = db + rank * 256, dm = db + (rank ? 0 : 1536);
#pragma unroll
        for (int k = k0; k < k1; k++) {
          if (k == 0 && O == 0) mma_rs64<O, 1, 2>(ct, h[0], h[1], h[2], h[3], dw, zero);
          else if (k < 14) mma_rs64<O, 1, 1>(ct, h[4 * k], h[4 * k + 1], h[4 * k + 2], h[4 * k + 3], k < 12 ? dw + k * 128 : dm + (k - 12) * 128);
          else if (k == 14 && fresh) mma_rs64<O, 1, 0>(ct, yf[0], yf[1], yf[2], yf[3], db + k * 128);
          else if (k == 14) mma_rs64<O, 1, 2>(ct, yf[0], yf[1], yf[2], yf[3], db + k * 128, zero);
          else mma_rs64<O, 1, 1>(ct, yf[4 * k - 56], yf[4 * k - 55], yf[4 * k - 54], yf[4 * k - 53], db + k * 128);
        }
      };
      uint4 pv[4];
      const uint32_t sgn = rank ? 0x80008000u : 0u;
      auto even_end = [&](int t, int k0, bool fresh) {
        wg_fence();
        tile_mma(IC<32>(), t, 14, 18, fresh);
        wg_commit();
        tile_mma(IC<0>(), t, k0, 14);
        wg_commit();
        tr();
        wg_wait<1>();
        tr();
        fence_regs<32, 32>(ct);
#pragma unroll
        for (int i = 0; i < 4; i++)
          pv[i] = make_uint4(pack_pin(ct[32 + 8 * i], ct[33 + 8 * i]) ^ sgn, pack_pin(ct[34 + 8 * i], ct[35 + 8 * i]) ^ sgn,
                             pack_pin(ct[36 + 8 * i], ct[37 + 8 * i]) ^ sgn, pack_pin(ct[38 + 8 * i], ct[39 + 8 * i]) ^ sgn);
      };
      auto staged = [&](int bar) {
        asm volatile("fence.proxy.async.shared::cta;" ::: "memory");
        __syncwarp();
        mbar_arrive_if(lane == 0, bars + 8 * (bar + wg));
      };
      const uint32_t peerA = mapa(bars + 8 * (B_AK + wg), rank ^ 1);
      auto ack = [&] { asm volatile("{\n.reg .pred p;\nsetp.eq.b32 p, %1, 0;\n@p mbarrier.arrive.shared::cluster.b64 _, [%0];\n}" ::"r"(peerA), "r"(lane) : "memory"); };
      auto odd_head = [&](int t) {
        tr();
        twait(bars + 8 * (B_FT + (t & 3)), t >> 2, t);
        wg_fence();
        tile_mma(IC<32>(), t, 0, OA);
        wg_commit();
        tr();
        if (t > 1) twait(bars + 8 * (B_AK + wg), ((t >> 1) + 1) & 1, 14);
        wg_wait<1>();
        tr();
        mbar_arrive_if(elect && t < 6, bars + 8 * (B_ET + t - 1));
        fence_regs<0, 32>(ct);
#pragma unroll
        for (int i = 0; i < 4; i++)
          asm volatile("st.shared.v4.u32 [%0], {%1,%2,%3,%4};" ::"r"(sb + (1 + 2 * wg) * TB + 28672 + w * 2048 + i * 512 + lane * 16),
                       "r"(add_bf2(pv[i].x, pack_bf16(ct[8 * i], ct[8 * i + 1]))), "r"(add_bf2(pv[i].y, pack_bf16(ct[8 * i + 2], ct[8 * i + 3]))),
                       "r"(add_bf2(pv[i].z, pack_bf16(ct[8 * i + 4], ct[8 * i + 5]))), "r"(add_bf2(pv[i].w, pack_bf16(ct[8 * i + 6], ct[8 * i + 7]))) : "memory");
        wg_fence();
        tile_mma(IC<32>(), t, OA, OA + 4);
        wg_commit();
        staged(B_HS);
      };
      asm volatile("barrier.cluster.wait.aligned;" ::: "memory");
      twait(bars + 8 * B_FT, 0, 0);
      wg_fence();
      tile_mma(IC<0>(), 0, 0, T0A);
      wg_commit();
      waitA(29 + wg);
      wg_wait<1>();
      mbar_arrive_if(elect, bars + 8 * (B_ET + 3));
      glu(cC, 32, 32, 0, 16);
      if (tid == 0) PROF_EV(6);
      if (tid == 128) PROF_EV(27);
      mbar_wait(bars + 8 * (j == 0 ? B_T : B_TL), 0);
      if (tid == 0) { PROF_EV(7); PROF_CK(45); }
      wg_fence();
      {
        const uint64_t dt = d128(dN + (OFF_T >> 4) + wg * 512), de = d128(dK + RING + (1 + wg) * 1024);
        mma_ss64<0, 1, 0>(ci, de, dt);
        mma_ss64<32, 1, 0>(ci, de + 512, dt);
#pragma unroll
        for (int k = 1; k < 4; k++) {
          mma_ss64<0, 1, 1>(ci, de + k * 2, dt + k * 128);
          mma_ss64<32, 1, 1>(ci, de + (512 + k * 2), dt + k * 128);
        }
        wg_commit();
      }
      tile_mma(IC<0>(), 0, T0A, T0B);
      wg_commit();
      wg_wait<1>();
      if (elect) asm volatile("mbarrier.arrive.shared::cluster.b64 _, [%0];" ::"r"(mapa(bars + 8 * B_RDY, rank ^ 1)) : "memory");
      mbar_arrive_if(elect, bars + 8 * (B_PZ + 1));
      fence_regs<0, 64>(ci);
#pragma unroll
      for (int i = 0; i < 16; i++) {
        const float gg = ((i & 1) ? g1 : g0) * (2.0f / (2048.0f * 512.0f));
        if (i & 2) yf[i] = pack_pin((ci[2 * i] - ci[28 + 2 * i]) * gg, (ci[2 * i + 1] - ci[29 + 2 * i]) * gg);
        else yf[i] = pack_pin((ci[2 * i] + ci[36 + 2 * i]) * gg, (ci[2 * i + 1] + ci[37 + 2 * i]) * gg);
      }
      even_end(0, T0B, true);
      if (tid == 0) PROF_EV(8);
      if (tid == 128) PROF_EV(28);
#pragma unroll 1
      for (int t = 1; t < 7; t += 2) {
        odd_head(t);
        tr();
        wg_fence();
        tile_mma(IC<32>(), t, OA + 4, 14);
        wg_commit();
        tr();
        if (t == 5) { fetch(pv, 2); ack(); }
        twait(bars + 8 * (B_FT + ((t + 1) & 3)), (t + 1) >> 2, t + 1);
        wg_fence();
        tile_mma(IC<0>(), t + 1, 0, TH);
        wg_commit();
        tr();
        wg_wait<1>();
        tr();
        mbar_arrive_if(elect && t < 5, bars + 8 * (B_ET + t));
        auto sum4 = [&] {
          fence_regs<32, 32>(ct);
#pragma unroll
          for (int i = 0; i < 4; i++)
            pv[i] = make_uint4((add_bf2(pv[i].x, pack_bf16(ct[32 + 8 * i], ct[33 + 8 * i])) & ~1u) | tag, add_bf2(pv[i].y, pack_bf16(ct[34 + 8 * i], ct[35 + 8 * i])),
                               add_bf2(pv[i].z, pack_bf16(ct[36 + 8 * i], ct[37 + 8 * i])), add_bf2(pv[i].w, pack_bf16(ct[38 + 8 * i], ct[39 + 8 * i])));
        };
        if (t == 5) {
          const int owner = rb * 8 + 2 * ((q4 + 3) & 3) + rank;
          uint4* dst = ws->part + (size_t)(owner * 3 + 2) * 1024 + fo;
          sum4();
#pragma unroll
          for (int i = 0; i < 4; i++)
            asm volatile("st.relaxed.gpu.global.v4.u32 [%0], {%1,%2,%3,%4};" ::"l"(dst + i * 32), "r"(pv[i].x), "r"(pv[i].y), "r"(pv[i].z), "r"(pv[i].w) : "memory");
          hint_add_if(lane == 0, &ws->cntP[32 * owner + 8 * (2 + wg)]);
        } else {
          fetch(pv, t >> 1); ack();
        }
        tr();
        wg_fence();
        tile_mma(IC<0>(), t + 1, TH, EB);
        wg_commit();
        tr();
        if (t != 5) {
          sum4();
#pragma unroll
          for (int i = 0; i < 4; i++)
            asm volatile("st.shared.v4.u32 [%0], {%1,%2,%3,%4};" ::"r"(sb + OFF_Z - (t >> 1) * U + fo * 16 + i * 512), "r"(pv[i].x), "r"(pv[i].y), "r"(pv[i].z), "r"(pv[i].w) : "memory");
        }
        tr();
        even_end(t + 1, EB, false);
        if (t != 5) staged(B_HH + t - 1);
      }
      {
        uint4 p1[4], p2[4];
        auto acc4 = [&](uint4 (&d)[4], const uint4 (&a)[4]) {
#pragma unroll
          for (int i = 0; i < 4; i++) { d[i].x = add_bf2(d[i].x, a[i].x); d[i].y = add_bf2(d[i].y, a[i].y); d[i].z = add_bf2(d[i].z, a[i].z); d[i].w = add_bf2(d[i].w, a[i].w); }
        };
        auto add32 = [&](const uint4 (&a)[4]) {
#pragma unroll
          for (int i = 0; i < 4; i++) {
            const uint32_t u[4] = {a[i].x, a[i].y, a[i].z, a[i].w};
#pragma unroll
            for (int e = 0; e < 4; e++) { ct[32 + 8 * i + 2 * e] += bf_lo(u[e]); ct[33 + 8 * i + 2 * e] += bf_hi(u[e]); }
          }
        };
        odd_head(7);
        fetch(pv, 4);
        fetch(p1, 5);
        wg_fence();
        tile_mma(IC<32>(), 7, OA + 4, OB);
        wg_commit();
        uint32_t bad = 0;
#pragma unroll
        for (int i = 0; i < 4; i++) { bad |= (pv[i].x ^ tag) | (p1[i].x ^ tag); pv[i].x &= ~1u; p1[i].x &= ~1u; }
        acc4(pv, p1);
        fetch(p1, 3); ack();
        wg_fence();
        tile_mma(IC<32>(), 7, OB, 14);
        wg_commit();
        if (tid == 0) { PROF_EV(9); PROF_CK(46); }
        if (tid == 128) PROF_EV(29);
        fetch(p2, 6);
        if (tid == 0) PROF_EV(24);
        wg_wait<0>();
        fence_regs<32, 32>(ct);
#pragma unroll
        for (int i = 0; i < 4; i++) bad |= p2[i].x ^ tag;
        if (__any_sync(0xffffffffu, bad & 1)) {
          const uint4* src = ws->part + (size_t)(rb * 8 + j) * 3 * 1024 + fo;
          uint4 p0[4];
          int n = 0;
          do {
            bad = 0;
#pragma unroll
            for (int i = 0; i < 4; i++) {
              pv[i] = ld_x4(src + i * 32); p0[i] = ld_x4(src + 1024 + i * 32); p2[i] = ld_x4(src + 2048 + i * 32);
              bad |= (pv[i].x ^ tag) | (p0[i].x ^ tag) | (p2[i].x ^ tag);
            }
            if (++n > (1 << 21)) __trap();
          } while (__any_sync(0xffffffffu, bad & 1));
#pragma unroll
          for (int i = 0; i < 4; i++) { pv[i].x &= ~1u; p0[i].x &= ~1u; }
          acc4(pv, p0);
        }
#pragma unroll
        for (int i = 0; i < 4; i++) p2[i].x &= ~1u;
        acc4(p1, p2);
        add32(pv); add32(p1);
#pragma unroll
        for (int i = 0; i < 4; i++)
          pv[i] = make_uint4(pack_bf16(ct[32 + 8 * i], ct[33 + 8 * i]), pack_bf16(ct[34 + 8 * i], ct[35 + 8 * i]), pack_bf16(ct[36 + 8 * i], ct[37 + 8 * i]), pack_bf16(ct[38 + 8 * i], ct[39 + 8 * i]));
        if (tid == 0) PROF_EV(14);
        const uint32_t stg = sb + OFF_T + warp * 2048;
        const int mr = (lane & 7) + ((lane >> 3) & 1) * 8, mc = lane >> 4;
#pragma unroll
        for (int i = 0; i < 4; i++)
          asm volatile("stmatrix.sync.aligned.m8n8.x4.shared.b16 [%0], {%1,%2,%3,%4};" ::"r"(stg + mr * 128 + (((2 * i + mc) ^ (mr & 7)) << 4)), "r"(pv[i].x),
                       "r"(pv[i].y), "r"(pv[i].z), "r"(pv[i].w) : "memory");
        __syncwarp();
#pragma unroll
        for (int i = 0; i < 4; i++) {
          const int r = 4 * i + (lane >> 3), c = lane & 7;
          const uint4 v = *(const uint4*)(smem + OFF_T + warp * 2048 + r * 128 + ((c ^ (r & 7)) << 4));
          *(uint4*)(out + (size_t)(2 * rb + wg + 32 * (16 * w + r)) * 512 + 64 * (q4 + 4 * rank) + 8 * c) = v;
        }
      }
      if (tid == 0) { PROF_EV(15); PROF_CK(41); }
      if (tid == 128) PROF_EV(30);
    }
  } else if (warp < 12) {
    asm volatile("setmaxnreg.dec.sync.aligned.u32 104;");
    asm volatile("barrier.cluster.arrive.relaxed.aligned;" ::: "memory");
    const int t = tid - 256, w = warp - 8;
    const uint32_t ep = ld_x1(&ws->epoch[blockIdx.x * 8]);
    const uint32_t tag = (ep + 1) & 1;
    auto w_issue = [&](const CUtensorMap* m) {

      if (elect_one()) { mbar_expect_tx(bars + 8 * (B_WR + w), 3072); tma4d(sb + OFF_T + w * 3072, m, bars + 8 * (B_WR + w), 32 * j, 0, 4 * (rb & 1) + w, rb >> 1); }

          __syncwarp();
    };
    auto gate_rows = [&] {
      const int r = 16 * j + 4 * w + (lane >> 3);
      const uint4* pg = (const uint4*)gate_w + (lane & 7);
      {
        float a = 0.f;
        asm volatile("bar.sync 4, 256;" ::: "memory");
#pragma unroll 1
        for (int hf = 0; hf < 2; hf++) {
          uint4 v[4], u[4];
#pragma unroll
          for (int kb = 0; kb < 4; kb++) v[kb] = __ldg(pg + (4 * hf + kb) * 8);
          mbar_wait(bars + 8 * (B_FE + 1 + 2 * hf), 0);
          if (hf) w_issue(&maps.wr);
#pragma unroll
          for (int kb = 0; kb < 4; kb++) u[kb] = *(const uint4*)(smem + (4 * hf + kb) * U + r * 128 + (((lane ^ r) & 7) << 4));
#pragma unroll
          for (int kb = 0; kb < 4; kb++) {
            const uint32_t uu[4] = {u[kb].x, u[kb].y, u[kb].z, u[kb].w}, vv[4] = {v[kb].x, v[kb].y, v[kb].z, v[kb].w};
#pragma unroll
            for (int e = 0; e < 4; e++) {
              uint32_t pr;
              asm("mul.rn.bf16x2 %0, %1, %2;" : "=r"(pr) : "r"(uu[e]), "r"(vv[e]));
              a += bf_lo(pr) + bf_hi(pr);
            }
          }
        }
#pragma unroll
        for (int o = 4; o; o >>= 1) a += __shfl_xor_sync(0xffffffffu, a, o);
        if ((lane & 7) == 0)
          asm volatile("st.relaxed.gpu.global.u32 [%0], %1;" ::"l"(ws->gate + rb * 128 + r),
                       "r"(pack_bf16(0.f, __fdividef(1.0f, 1.0f + __expf(-bf_lo(pack_bf16(a, 0.f))))) | tag) : "memory");
        if (t == 0) PROF_EV(18);
      }
    };
    {
      const int g = lane >> 2, q = lane & 3;
      uint32_t wf[32];
      if (!helper) {
        gate_rows();
        const uint32_t wa = sb + OFF_T + w * (3072 + 2) + (rb & 1) * 8 + q * 96 + g * 4, wb[2] = {wa + (rb & 1) * 32, wa + 32 - (rb & 1) * 32};
#pragma unroll 1
        for (int ri = 0; ri < 2; ri++) {
          mbar_wait(bars + 8 * (B_WR + w), ri);
#pragma unroll
          for (int n2 = 0; n2 < 32 / WB; n2++) {
            uint32_t v[WB];
#pragma unroll
            for (int i = 0; i < WB; i++) {
              const int e = n2 * WB + i;
              asm volatile("ld.shared.u16 %0, [%1];" : "=r"(v[i]) : "r"(wb[e & 1] + ((e >> 1) & 7) * 384 + (e >> 4) * 2) : "memory");
            }
#pragma unroll
            for (int i = 0; i < WB; i++) wf[n2 * WB + i] = __byte_perm(wf[n2 * WB + i], v[i], 0x5432);
            if (WSLEEP) { asm volatile("nanosleep.u32 %0;" ::"r"(WSLEEP + (v[WB - 1] >> 16)) : "memory"); }
          }
          __syncwarp();
          if (ri == 0) w_issue(&maps.wi);
        }
        asm volatile("bar.sync 1, 128;" ::: "memory");
        if (t == 0) PROF_EV(11);
      } else {
        asm volatile("bar.sync 4, 256;" ::: "memory");
        hint_wait(&ws->cntW[0], (ep + 1) * 128u);
        const uint32_t t0 = (uint32_t)clock();
#pragma unroll 1
        for (;;) {
          uint32_t bad = 0;
#pragma unroll
          for (int i = 0; i < 32; i++) {
            const float2 v = ld_x2((const float2*)ws->Wh + (i >> 4) * 2048 + 16 * w + g + 8 * (i & 1) + 64 * q + ((i >> 1) & 7) * 256);
            wf[i] = __float_as_uint(v.x); bad |= __float_as_uint(v.y) ^ tag;
          }
          if (!__any_sync(0xffffffffu, bad & 1)) break;
          spin_guard(t0);
        }
        if (t == 0) PROF_EV(11);
      }
      if (w == 0 && elect_one()) { mbar_expect_tx(bars + 8 * B_W, 8192); bulk_load(sb + OFF_D, dtab, 8192, bars + 8 * B_W); }
      asm volatile("barrier.cluster.wait.aligned;" ::: "memory");
      mbar_wait(bars + 8 * B_W, 0);
      mbar_wait(bars + 8 * B_HX, 0);
      if (t == 0) PROF_EV(12);
      const uint32_t dd = (sb & 0x3FFFF) >> 4;
      const uint64_t dF = d128((dd + (OFF_D >> 4)) | (512u << 16)), dI = d128((dd + (OFF_D >> 4)) | (1u << 16)), dA = d128((dd + (OFF_XB >> 4)) | (512u << 16));
      float az[32];
      const int zero = blockIdx.x >> 16;
      uint32_t pf[32];
#pragma unroll
      for (int mt = 0; mt < 2; mt++) {
        wg_fence();
        if (mt == 0) mma_ss64<0, 3, 0>(az, dA, dF);
        else mma_ss64<0, 3, 2>(az, dA + 512, dF, zero);
#pragma unroll
        for (int k = 1; k < 4; k++) mma_ss64<0, 3, 1>(az, dA + (mt * 512 + k * 128), dF + k * 128);
        wg_commit();
        wg_wait<0>();
        fence_regs<0, 32>(az);
#pragma unroll
        for (int i = 0; i < 16; i++) {
          const float wr = bf_lo(wf[16 * mt + i]), wi = bf_hi(wf[16 * mt + i]);
          pf[16 * mt + i] = pack_pin(fmaf(az[2 * i], wr, -az[2 * i + 1] * wi), fmaf(az[2 * i], wi, az[2 * i + 1] * wr));
        }
      }
      if (t == 0) PROF_EV(16);
      {
        const int m = lane >> 3, r = lane & 7;
        const int sl = 2 * (m >> 1) + ((r >> 1) & 1) + 4 * (r >> 2);
        const uint32_t a0 = sb + OFF_XB + w * 4096 + sl * 64 + (((((m ^ rb) & 1) * 2 + (r & 1)) ^ (sl >> 1)) << 4);
        uint32_t pk[16];
#pragma unroll
        for (int mt = 0; mt < 3; mt++) {
          if (mt < 2) {
            wg_fence();
            mma_rs64<0, 0, 2>(az, pf[16 * mt], pf[16 * mt + 1], pf[16 * mt + 2], pf[16 * mt + 3], dI, mt ? (int)helper : zero);
#pragma unroll
            for (int k = 1; k < 4; k++) mma_rs64<0, 0, 1>(az, pf[16 * mt + 4 * k], pf[16 * mt + 4 * k + 1], pf[16 * mt + 4 * k + 2], pf[16 * mt + 4 * k + 3], dI + k * 2);
            wg_commit();
          }
          if (mt > 0 && !helper) {
#pragma unroll
            for (int i = 0; i < 4; i++) stsm4t(a0 + (mt - 1) * 2048 + i * 512, pk[4 * i], pk[4 * i + 1], pk[4 * i + 2], pk[4 * i + 3]);
          }
          if (mt < 2) {
            wg_wait<0>();
            fence_regs<0, 32>(az);
#pragma unroll
            for (int i = 0; i < 16; i++) pk[i] = pack_pin(az[2 * i], az[2 * i + 1]);
          }
        }
      }
      if (helper) {
#pragma unroll
        for (int i = 0; i < 16; i++) {
          const int n = i >> 1, s0 = 8 * (n >> 1) + 2 * (n & 1) + (q & 1) + 4 * (q >> 1);
          if ((n & 1) == (int)(blockIdx.x & 1)) st_u2(ws->Ts + s0 * 64 + 16 * w + g + 8 * (i & 1), pack_bf16(az[2 * i], az[2 * i + 1]), tag);
        }
        __syncwarp();
        hint_add_if(lane == 0, &ws->cntH[0]);
        if (t == 0) { ws->epoch[blockIdx.x * 8] = ep + 1; PROF_EV(13); }
      } else {
        asm volatile("fence.proxy.async.shared::cta;" ::: "memory");
        __syncwarp();
        if (elect_one()) {
          if (t == 0) PROF_EV(17);
          if (SPACE) __nanosleep(SPACE * w);
          asm volatile("cp.async.bulk.tensor.4d.global.shared::cta.bulk_group [%0, {%2, %3, %4, %5}], [%1];" ::"l"(&maps.ts), "r"(sb + OFF_XB + w * 4096),
                       "r"(32 * rank), "r"(0), "r"(2 * q4), "r"(4 * rb + w) : "memory");
          bulk_done_signal(&ws->cntT[32 * q4]);
          asm volatile("mbarrier.arrive.shared::cluster.b64 _, [%0];" ::"r"(mapa(bars + 8 * B_RD0, rank ^ 1)) : "memory");
          if (t == 96) PROF_EV(13);
        }
        __syncwarp();
        if (j == 0) {
          hint_wait(&ws->cntH[0], (ep + 1) * 8u);
          const uint32_t t0 = (uint32_t)clock();
          float2 v;
          do { v = ld_x2((const float2*)ws->Ts + 2 * rb * 64 + t); spin_guard(t0); } while (__any_sync(0xffffffffu, (__float_as_uint(v.y) ^ tag) & 1));
          mbar_wait(bars + 8 * B_TL, 0);
          const uint32_t u = __float_as_uint(v.x);
          *(uint16_t*)(smem + OFF_T + t * 128 + ((t & 7) << 4)) = (uint16_t)u;
          *(uint16_t*)(smem + OFF_T + t * 128 + (((t & 7) ^ 1) << 4)) = (uint16_t)(u >> 16);
          asm volatile("fence.proxy.async.shared::cta;" ::: "memory");
          __syncwarp();
          mbar_arrive_if(lane == 0, bars + 8 * B_T);
        }
        if (elect_one()) {
          if (w < 2) part_load(2 + w, ep + 1);
          else {
#pragma unroll 1
            for (int z = 0; z < 2; z++) {
              const int owner = rb * 8 + 2 * ((q4 + z + 1) & 3) + rank;
              mbar_wait(bars + 8 * (B_HH + 2 * z + w - 2), 0);
              asm volatile("cp.async.bulk.global.shared::cta.bulk_group [%0], [%1], 8192;" ::"l"(ws->part + (size_t)(owner * 3 + z) * 1024 + (w - 2) * 512),
                           "r"(sb + OFF_Z - z * U + (w - 2) * 8192) : "memory");
              bulk_done_signal(&ws->cntP[32 * owner + 8 * z]);
            }
          }
        }
      }
    }
  } else {
    asm volatile("setmaxnreg.dec.sync.aligned.u32 24;");
    auto xf_load = [&](int q) {
      const uint32_t fb = bars + 8 * (B_FX + q);
      mbar_expect_tx(fb, U + 8192);
      tma3d(sb + q * U, &maps.x, fb, 64 * q, 0, 2 * rb);
      if (q >= 4) mbar_wait(bars + 8 * (B_FE + ((q - 4) >> 1)), 0);
      tma2d(sb + OFF_XB + (q & 3) * 8192, &maps.ft, fb, 64 * q, 64 * j);
    };
    if (elect_one()) {
      if (warp == 14) {
#pragma unroll
        for (int i = 0; i < B_FT; i++) mbar_init(bars + 8 * i, 1);
        asm volatile("fence.mbarrier_init.release.cluster;" ::: "memory");
        if (!helper) {
#pragma unroll 1
          for (int n = 0; n < 2; n++) {
            const uint32_t fb = bars + 8 * (B_FA + n);
            xf_load(2 * n); xf_load(2 * n + 1);
            mbar_expect_tx(fb, U);
            tma2d(sb + OFF_RING + n * U, &maps.g64, fb, f_full, 64 * n);
            tma2d(sb + OFF_RING + n * U + 8192, &maps.u64, fb, f_full, 64 * n);
          }
        }
      } else if (warp == 15) {
#pragma unroll
        for (int i = B_FT; i < NBAR; i++) mbar_init(bars + 8 * i, i < B_EA ? 1 : i < B_T ? 2 : 4);
#pragma unroll
        for (int i = 0; i < 8; i++) mbar_expect_tx(bars + 8 * (B_Z + i), U / 2);
        asm volatile("fence.mbarrier_init.release.cluster;" ::: "memory");
        asm volatile("fence.proxy.async.shared::cta;" ::: "memory");
      }
    }
    __syncwarp();
    asm volatile("bar.arrive 0, 384;" ::: "memory");
    asm volatile("bar.arrive 4, 256;" ::: "memory");
    __syncwarp();
    asm volatile("barrier.cluster.arrive.relaxed.aligned;" ::: "memory");
    asm volatile("bar.sync 3, 128;" ::: "memory");
    if (warp == 15 && !helper) {
        mbar_wait(bars + 8 * B_FE, 0);
        const uint32_t tag = (ld_x1(&ws->epoch[blockIdx.x * 8]) + 1) & 1;
        const int c = lane >> 4, jj = 16 * blockIdx.x + (lane & 15), jm = (2048 - jj) & 2047;
        const unsigned short* pr = (const unsigned short*)w_r + 256 * c;
        const unsigned short* pi = (const unsigned short*)w_i + 256 * c;
        const float wr = 0.25f * (bf_lo(__ldg(pr + jj * 257)) + bf_lo(__ldg(pr + jm * 257)));
        const float wi = 0.25f * (bf_lo(__ldg(pi + jj * 257)) - bf_lo(__ldg(pi + jm * 257)));
        st_u2(ws->Wh + c * 2048 + jj, c ? pack_bf16(-wi, wr) : pack_bf16(wr, wi), tag);
        __syncwarp();
        hint_add_if(lane == 0, &ws->cntW[0]);
        mbar_wait(bars + 8 * B_XS, 0);
        const uint32_t t0 = (uint32_t)clock();
        uint4 v;
        do { v = ld_x4(ws->gate + rb * 128 + 4 * lane); spin_guard(t0); } while (__any_sync(0xffffffffu, ((v.x ^ tag) | (v.y ^ tag) | (v.z ^ tag) | (v.w ^ tag)) & 1));
        *(uint4*)(smem + OFF_G + lane * 16) = v;
        __syncwarp();
        mbar_arrive_if(lane < 4, bars + 8 * B_G);
      }
    if ((!helper || warp == 15) && elect_one()) {
      if (warp < 14) {
        const int p = warp - 12;
#pragma unroll 1
        for (int i = 4 + p; i < 14; i += 2) asm volatile("prefetch.tensormap [%0];" ::"l"((const char*)&maps + i * 128) : "memory");
#pragma unroll 1
        for (int n = 2; n < 31; n++) {
          const bool table = n == 4 || n >= 29;
          const bool half = n >= 17 && n < 21;
          const int q = n < 4 ? n : n < 17 ? n - 1 : n - 5;
          const CUtensorMap* m = table ? &maps.e : half ? &maps.g32 + p : &maps.g64 + p;
          const int c0 = table ? 0 : half ? f_half : f_full + 64 * (q >> 3);
          const int c1 = table ? (2 * rb + ((n & 1) ^ 1)) * 128 + 64 * p : half ? 128 * (n - 17) : 64 * (q & 7);
          const uint32_t fb = bars + 8 * (B_FA + (n & 3)), dst = sb + OFF_RING + (n & 3) * U + p * 8192;
          if (n < 4) mbar_wait(bars + 8 * (B_FE + n - 2), 0);
          else mbar_wait(bars + 8 * (B_EA + (n & 3)), ((n >> 2) & 1) ^ 1);
          tma2d(dst, m, fb, c0, c1);
          if (p == 0) mbar_expect_tx(fb, U);
        }
        asm volatile("barrier.cluster.wait;" ::: "memory");
#pragma unroll 1
        for (int z = 0; z < 4; z++) {
          if (z < 2) mbar_wait(bars + 8 * (z ? B_RDY : B_RD0), 0);
          const uint32_t dst = mapa(sb + OFF_Z - z * U + p * 8192, rank ^ 1), bar = mapa(bars + 8 * (B_Z + 2 * z + p), rank ^ 1);
          mbar_wait(bars + 8 * (B_HS + p), z & 1);
          asm volatile("cp.async.bulk.shared::cluster.shared::cta.mbarrier::complete_tx::bytes [%0], [%1], 8192, [%2];" ::"r"(dst),
                       "r"(sb + (1 + 2 * p) * TB + 28672), "r"(bar) : "memory");
        }
        mbar_wait(bars + 8 * (B_AK + p), 1);
      } else if (warp == 15) {
        const unsigned ep1 = ld_x1(&ws->epoch[blockIdx.x * 8]) + 1;
        flag_wait(&ws->cntX[helper ? 0 : 32 * j], ep1 * 16u);
        PROF_EV(22);
        mbar_expect_tx(bars + 8 * B_HX, U);
        bulk_load(sb + OFF_XB, ws->X + (size_t)(helper ? 128 : 16 * j + rb) * 8192, U, bars + 8 * B_HX);
        if (!helper) {
          flag_wait(&ws->cntT[32 * q4], ep1 * 128u);
          PROF_EV(23);
          mbar_expect_tx(bars + 8 * B_TL, U);
          tma3d(sb + OFF_T, &maps.t, bars + 8 * B_TL, 64 * j, 0, 2 * rb);
          part_load(0, ep1); part_load(1, ep1);
          ws->epoch[blockIdx.x * 8] = ep1;
        }
      } else {
#pragma unroll 1
        for (int q = 4; q < 8; q++) xf_load(q);
        mbar_wait(bars + 8 * (B_FE + 2), 0);
        mbar_expect_tx(bars + 8 * B_E0, U);
        tma2d(sb + OFF_XB, &maps.e, bars + 8 * B_E0, 0, 2 * rb * 128);
        tma2d(sb + OFF_XB + 8192, &maps.e, bars + 8 * B_E0, 0, 2 * rb * 128 + 64);
#pragma unroll 1
        for (int h2 = 0; h2 < 2; h2++) {
          const int s0 = 2 * rb + h2, sg = (s0 & ~6) | ((s0 & 2) << 1) | ((s0 & 4) >> 1);
          mbar_wait(bars + 8 * (B_XS + h2), 0);
#pragma unroll 1
          for (int c = 0; c < 2; c++) {
            asm volatile("cp.async.bulk.tensor.4d.global.shared::cta.bulk_group [%0, {%2, %3, %4, %5}], [%1];" ::"l"(&maps.xs),
                         "r"(sb + OFF_XB + h2 * 8192 + c * 4096), "r"(0), "r"(sg), "r"(0), "r"(16 * j + 8 * c) : "memory");
            if (j == 0)
              asm volatile("cp.async.bulk.global.shared::cta.bulk_group [%0], [%1], 256;" ::"l"(ws->X + 128 * 8192 + c * 4096 + sg * 128),
                           "r"(sb + OFF_SP + h2 * 512 + c * 256) : "memory");
            if (SPACE && h2 + c < 2) __nanosleep(SPACE);
          }
        }
        bulk_done_signal(&ws->cntX[32 * j]);
        PROF_EV(20);
#pragma unroll 1
        for (int t = 0; t < 8; t++) {
          const int col = 64 * (((q4 + 1 + (t >> 1)) & 3) + 4 * ((t & 1) ? rank : 1 - rank));
          const uint32_t fb = bars + 8 * (B_FT + (t & 3)), dst = sb + (t & 3) * TB;
          mbar_wait(bars + 8 * (B_ET + (t < 3 ? t + 1 : t & 3)), t >> 2);
          mbar_expect_tx(fb, (t & 1) ? 28672 : TB);
          tma2d(dst, &maps.d224, fb, col, 224 * j);
          if (!(t & 1)) tma3d(dst + 28672, &maps.fg, fb, col ^ 256, 16 * rank, 4 * q4);
        }
      }
    }
  }
}

typedef CUresult (*EncodeFn)(CUtensorMap*, CUtensorMapDataType, cuuint32_t, void*, const cuuint64_t*, const cuuint64_t*, const cuuint32_t*,
                             const cuuint32_t*, CUtensorMapInterleave, CUtensorMapSwizzle, CUtensorMapL2promotion, CUtensorMapFloatOOBfill);

static void encode(EncodeFn f, CUtensorMap* m, const void* base, int rank, const cuuint64_t* dims, const cuuint64_t* strides, const cuuint32_t* box,
                   CUtensorMapSwizzle sw) {
  cuuint32_t es[5] = {1, 1, 1, 1, 1};
  f(m, CU_TENSOR_MAP_DATA_TYPE_BFLOAT16, rank, (void*)base, dims, strides, box, es, CU_TENSOR_MAP_INTERLEAVE_NONE, sw,
    CU_TENSOR_MAP_L2_PROMOTION_L2_128B, CU_TENSOR_MAP_FLOAT_OOB_FILL_NONE);
}

extern "C" void kernel_launch(void* const* d_in, const int* in_sizes, int n_in, void* d_out, int out_size) {
  (void)in_sizes; (void)n_in; (void)out_size;
  const __nv_bfloat16* x = (const __nv_bfloat16*)d_in[0];
  const __nv_bfloat16* w_r = (const __nv_bfloat16*)d_in[1];
  const __nv_bfloat16* w_i = (const __nv_bfloat16*)d_in[2];
  const __nv_bfloat16* Wg = (const __nv_bfloat16*)d_in[4];
  const __nv_bfloat16* Wu = (const __nv_bfloat16*)d_in[5];
  const __nv_bfloat16* Wd = (const __nv_bfloat16*)d_in[6];
  const __nv_bfloat16* gw = (const __nv_bfloat16*)d_in[7];

  void* fp = nullptr; cudaDriverEntryPointQueryResult qr;
  cudaGetDriverEntryPoint("cuTensorMapEncodeTiled", &fp, cudaEnableDefault, &qr);
  EncodeFn enc = (EncodeFn)fp;
  void *pFT, *pET, *pDT, *pW;
  cudaGetSymbolAddress(&pDT, g_DT); cudaGetSymbolAddress(&pW, g_work);
  void *pX = ((Work*)pW)->X, *pT = ((Work*)pW)->T;
  cudaGetSymbolAddress(&pFT, g_FT); cudaGetSymbolAddress(&pET, g_ET);

  Maps mp;
  const CUtensorMapSwizzle S128 = CU_TENSOR_MAP_SWIZZLE_128B, S64 = CU_TENSOR_MAP_SWIZZLE_64B;
  { cuuint64_t d[3] = {512, 64, 32}, s[2] = {32768, 1024}; cuuint32_t b[3] = {64, 64, 2}; encode(enc, &mp.x, x, 3, d, s, b, S128); }
  { cuuint64_t d[2] = {512, 512}, s[1] = {1024}; cuuint32_t b[2] = {64, 64}; encode(enc, &mp.ft, pFT, 2, d, s, b, S128); }
  { cuuint64_t d[4] = {128, 32, 2, 129}, s[3] = {256, 8192, 16384}; cuuint32_t b[4] = {128, 1, 2, 8}; encode(enc, &mp.xs, pX, 4, d, s, b, CU_TENSOR_MAP_SWIZZLE_NONE); }
  { cuuint64_t d[4] = {64, 32, 8, 64}, s[3] = {65536, 128, 1024}; cuuint32_t b[4] = {32, 32, 2, 1}; encode(enc, &mp.ts, pT, 4, d, s, b, S64); }
  { cuuint64_t d[3] = {512, 32, 16}, s[2] = {1024, 32768}; cuuint32_t b[3] = {64, 16, 4}; encode(enc, &mp.fg, pFT, 3, d, s, b, S128); }
  { cuuint64_t d[3] = {512, 64, 32}, s[2] = {1024, 65536}; cuuint32_t b[3] = {64, 64, 2}; encode(enc, &mp.t, pT, 3, d, s, b, S128); }
  { cuuint64_t d[2] = {64, 4096}, s[1] = {128}; cuuint32_t b[2] = {64, 64}; encode(enc, &mp.e, pET, 2, d, s, b, S128); }
  { cuuint64_t d[2] = {1792, 512}, s[1] = {3584}; cuuint32_t b[2] = {64, 64}, b2[2] = {32, 128};
    encode(enc, &mp.g64, Wg, 2, d, s, b, S128); encode(enc, &mp.u64, Wu, 2, d, s, b, S128);
    encode(enc, &mp.g32, Wg, 2, d, s, b2, S64); encode(enc, &mp.u32, Wu, 2, d, s, b2, S64); }
  { cuuint64_t d[2] = {512, 1792}, s[1] = {1024}; cuuint32_t b[2] = {64, 224}; encode(enc, &mp.d224, Wd, 2, d, s, b, S128); }
  { cuuint64_t d[4] = {264, 32, 8, 8}, s[3] = {32896, 512, 4112}; cuuint32_t b[4] = {48, 32, 1, 1};
    encode(enc, &mp.wr, w_r, 4, d, s, b, CU_TENSOR_MAP_SWIZZLE_NONE); encode(enc, &mp.wi, w_i, 4, d, s, b, CU_TENSOR_MAP_SWIZZLE_NONE); }

  cudaFuncSetAttribute(fused_kernel, cudaFuncAttributeMaxDynamicSharedMemorySize, SMEM_BYTES);
  fused_kernel<<<NCTA, 512, SMEM_BYTES>>>((Work*)pW, (const uint16_t*)pDT, w_r, w_i, gw, x, (__nv_bfloat16*)d_out, mp);
}
```

```cpp
#include <cuda_runtime.h>
#include <cuda_bf16.h>
#include <cuda.h>
#include <stdint.h>

namespace tbl {
constexpr double PI = 3.14159265358979323846264338327950288;
constexpr double sin_s(double x) { double t = x, s = x; for (int n = 1; n < 12; n++) { t *= -x * x / ((2 * n) * (2 * n + 1)); s += t; } return s; }
constexpr double cos_s(double x) { double t = 1, s = 1; for (int n = 1; n < 12; n++) { t *= -x * x / ((2 * n - 1) * (2 * n)); s += t; } return s; }
constexpr double cos2048(int m) {
  m &= 2047; if (m > 1024) m = 2048 - m;
  bool neg = false; if (m > 512) { m = 1024 - m; neg = true; }
  double v = (m <= 256) ? cos_s(2 * PI * m / 2048) : sin_s(2 * PI * (512 - m) / 2048);
  return neg ? -v : v;
}
constexpr uint16_t to_bf16(double v) {
  if (v == 0) return 0;
  uint16_t s = 0; if (v < 0) { s = 0x8000; v = -v; }
  int e = 0; while (v >= 2) { v /= 2; e++; } while (v < 1) { v *= 2; e--; }
  double m = (v - 1) * 128; int mi = (int)m; double fr = m - mi;
  if (fr > 0.5 || (fr == 0.5 && (mi & 1))) mi++;
  if (mi == 128) { mi = 0; e++; }
  return (uint16_t)(s | ((e + 127) << 7) | mi);
}
struct CosT { uint16_t v[2048]; constexpr CosT() : v() { for (int i = 0; i < 2048; i++) v[i] = to_bf16(cos2048(i)); } };
struct alignas(1024) FT {
  uint16_t v[512 * 512];
  constexpr FT() : v() {
    CosT c;
    for (int r = 0; r < 512; r++) {
      int k = (r >> 5) * 16 + 2 * (r & 7) + ((r >> 4) & 1), e = (r >> 3) & 1;
      int mul = 4 * k, add = e ? 512 : 0;
      if (k == 0 && e == 1) { mul = 1024; add = 0; }
      for (int d = 0; d < 512; d++) v[r * 512 + d] = c.v[(d * mul + add) & 2047];
    }
  }
};
struct alignas(1024) ET {
  uint16_t v[2048 * 128];
  constexpr ET() : v() {
    CosT c;
    for (int s = 0; s < 2048; s++)
      for (int j = 0; j < 64; j++) {
        const int o = (s & 31) * 8192 + (s >> 5) * 64 + j;
        v[o] = c.v[(s * j) & 2047]; v[o + 4096] = c.v[(s * j + 512) & 2047];
      }
  }
};
struct alignas(1024) DT {
  uint16_t v[64 * 64];
  constexpr DT() : v() {
    CosT c;
    for (int r = 0; r < 64; r++)
      for (int n = 0; n < 64; n++) {
        const int sg = r >> 1, s0 = (sg & ~6) | ((sg & 2) << 1) | ((sg & 4) >> 1), e = r & 1, f = n & 1;
        const int m = 64 * s0 * (n >> 1) + (e == f ? 0 : e ? -512 : 512);
        v[r * 64 + (((n >> 3) ^ (r & 7)) << 3) + (n & 7)] = c.v[m & 2047];
      }
  }
};
}

__device__ constexpr tbl::FT g_FT = tbl::FT();
__device__ constexpr tbl::ET g_ET = tbl::ET();
__device__ constexpr tbl::DT g_DT = tbl::DT();

struct alignas(1024) Work {
  unsigned epoch[132 * 8];
  unsigned cntX[8 * 32], cntT[8 * 32], cntP[128 * 64], cntW[32], cntH[32];
  alignas(16) float gate[16 * 128];
  alignas(16) uint2 Wh[2 * 2048];
  alignas(16) uint2 Ts[32 * 64];
  alignas(1024) uint16_t X[129 * 8192];
  alignas(1024) uint16_t T[32 * 64 * 512];
  alignas(1024) uint4 part[128 * 4 * 1024];
};
__device__ Work g_work;
#define PROF_EV(i) do {} while (0)
#define PROF_CK(i) do {} while (0)

__device__ __forceinline__ uint32_t smem_u32(const void* p) { return (uint32_t)__cvta_generic_to_shared(p); }
__device__ __forceinline__ void mbar_init(uint32_t bar, uint32_t cnt) { asm volatile("mbarrier.init.shared::cta.b64 [%0], %1;" ::"r"(bar), "r"(cnt)); }
__device__ __forceinline__ void mbar_expect_tx(uint32_t bar, uint32_t bytes) { asm volatile("mbarrier.arrive.expect_tx.shared::cta.b64 _, [%0], %1;" ::"r"(bar), "r"(bytes) : "memory"); }
__device__ __forceinline__ void mbar_arrive(uint32_t bar) { asm volatile("mbarrier.arrive.shared::cta.b64 _, [%0];" ::"r"(bar) : "memory"); }
__device__ __forceinline__ bool elect_one() {
  uint32_t p;
  asm volatile("{\n.reg .pred p;\nelect.sync _|p, 0xffffffff;\nselp.u32 %0, 1, 0, p;\n}" : "=r"(p));
  return p;
}
__device__ __forceinline__ void mbar_arrive_if(bool p, uint32_t bar) {
  asm volatile("{\n.reg .pred p;\nsetp.ne.b32 p, %1, 0;\n@p mbarrier.arrive.shared::cta.b64 _, [%0];\n}" ::"r"(bar), "r"((int)p) : "memory");
}
__device__ __forceinline__ void hint_add_if(bool p, unsigned* a) {
  asm volatile("{\n.reg .pred p;\nsetp.ne.b32 p, %1, 0;\n@p red.relaxed.gpu.global.add.u32 [%0], 1;\n}" ::"l"(a), "r"((int)p) : "memory");
}
__device__ __forceinline__ bool mbar_try(uint32_t bar, uint32_t parity) {
  uint32_t ok;
  asm volatile("{\n.reg .pred p;\nmbarrier.test_wait.parity.shared::cta.b64 p, [%1], %2;\nselp.u32 %0, 1, 0, p;\n}" : "=r"(ok) : "r"(bar), "r"(parity) : "memory");
  return ok;
}
__device__ __forceinline__ void mbar_wait(uint32_t bar, uint32_t parity) {
  asm volatile(
      "{\n.reg .pred p;\n.reg .u32 n;\nmov.u32 n, 0;\n"
      "W_LOOP:\nmbarrier.try_wait.parity.shared::cta.b64 p, [%0], %1;\n@p bra W_DONE;\n"
      "add.u32 n, n, 1;\nsetp.lt.u32 p, n, 0x40000;\n@p bra W_LOOP;\ntrap;\nW_DONE:\n}" ::"r"(bar), "r"(parity) : "memory");
}
__device__ __forceinline__ void bulk_load(uint32_t dst, const void* src, uint32_t bytes, uint32_t bar) {
  asm volatile("cp.async.bulk.shared::cluster.global.mbarrier::complete_tx::bytes [%0], [%1], %2, [%3];" ::"r"(dst), "l"(src), "r"(bytes), "r"(bar) : "memory");
}
__device__ __forceinline__ void spin_guard(uint32_t t0) { if ((uint32_t)clock() - t0 > (1u << 30)) __trap(); }
__device__ __forceinline__ float2 ld_x2(const float2* p) { float2 v; asm volatile("ld.relaxed.gpu.global.v2.f32 {%0,%1}, [%2];" : "=f"(v.x), "=f"(v.y) : "l"(p) : "memory"); return v; }
__device__ __forceinline__ void st_u2(uint2* p, uint32_t a, uint32_t b) { asm volatile("st.relaxed.gpu.global.v2.u32 [%0], {%1,%2};" ::"l"(p), "r"(a), "r"(b) : "memory"); }
__device__ __forceinline__ uint32_t ld_x1(const void* p) { uint32_t v; asm volatile("ld.relaxed.gpu.global.u32 %0, [%1];" : "=r"(v) : "l"(p) : "memory"); return v; }
__device__ __forceinline__ uint4 ld_x4(const void* p) { uint4 v; asm volatile("ld.relaxed.gpu.global.v4.u32 {%0,%1,%2,%3}, [%4];" : "=r"(v.x), "=r"(v.y), "=r"(v.z), "=r"(v.w) : "l"(p) : "memory"); return v; }
__device__ __forceinline__ uint32_t mapa(uint32_t a, uint32_t cta) { uint32_t r; asm volatile("mapa.shared::cluster.u32 %0, %1, %2;" : "=r"(r) : "r"(a), "r"(cta)); return r; }
__device__ __forceinline__ void stsm4t(uint32_t a, uint32_t r0, uint32_t r1, uint32_t r2, uint32_t r3) {
  asm volatile("stmatrix.sync.aligned.m8n8.x4.trans.shared.b16 [%0], {%1,%2,%3,%4};" ::"r"(a), "r"(r0), "r"(r1), "r"(r2), "r"(r3) : "memory");
}
__device__ __forceinline__ void hint_add(unsigned* p) { asm volatile("red.relaxed.gpu.global.add.u32 [%0], 1;" ::"l"(p) : "memory"); }
__device__ __forceinline__ void hint_wait(const unsigned* p, unsigned target) {
  const uint32_t t0 = (uint32_t)clock();
  while ((int)(ld_x1(p) - target) < 0) spin_guard(t0);
}
__device__ __forceinline__ void bulk_done_signal(unsigned* p) {
  asm volatile("cp.async.bulk.commit_group;\ncp.async.bulk.wait_group 0;\nfence.proxy.async.global;" ::: "memory");
  hint_add(p);
}
__device__ __forceinline__ void flag_wait(const unsigned* p, unsigned target) {
  hint_wait(p, target);
  asm volatile("fence.proxy.async.global;" ::: "memory");
}
__device__ __forceinline__ void tma2d(uint32_t dst, const CUtensorMap* m, uint32_t bar, int c0, int c1) {
  asm volatile("cp.async.bulk.tensor.2d.shared::cluster.global.mbarrier::complete_tx::bytes [%0], [%1, {%3, %4}], [%2];" ::"r"(dst), "l"(m), "r"(bar), "r"(c0), "r"(c1) : "memory");
}
__device__ __forceinline__ void tma3d(uint32_t dst, const CUtensorMap* m, uint32_t bar, int c0, int c1, int c2) {
  asm volatile("cp.async.bulk.tensor.3d.shared::cluster.global.mbarrier::complete_tx::bytes [%0], [%1, {%3, %4, %5}], [%2];" ::"r"(dst), "l"(m), "r"(bar), "r"(c0), "r"(c1), "r"(c2) : "memory");
}
__device__ __forceinline__ void tma4d(uint32_t dst, const CUtensorMap* m, uint32_t bar, int c0, int c1, int c2, int c3) {
  asm volatile("cp.async.bulk.tensor.4d.shared::cluster.global.mbarrier::complete_tx::bytes [%0], [%1, {%3, %4, %5, %6}], [%2];" ::"r"(dst), "l"(m), "r"(bar), "r"(c0), "r"(c1), "r"(c2), "r"(c3) : "memory");
}
__device__ __forceinline__ void wg_fence() { asm volatile("wgmma.fence.sync.aligned;" ::: "memory"); }
__device__ __forceinline__ void wg_commit() { asm volatile("wgmma.commit_group.sync.aligned;" ::: "memory"); }
template <int N> __device__ __forceinline__ void wg_wait() { asm volatile("wgmma.wait_group.sync.aligned %0;" ::"n"(N) : "memory"); }
template <int O, int N, int NN> __device__ __forceinline__ void fence_regs(float (&d)[NN]) {
#pragma unroll
  for (int i = 0; i < N; i++) asm volatile("" : "+f"(d[O + i])::"memory");
}
__device__ __forceinline__ uint32_t pack_bf16(float lo, float hi) {
  uint32_t r; asm("cvt.rn.bf16x2.f32 %0, %1, %2;" : "=r"(r) : "f"(hi), "f"(lo)); return r;
}
__device__ __forceinline__ uint32_t pack_pin(float lo, float hi) {
  uint32_t r; asm volatile("cvt.rn.bf16x2.f32 %0, %1, %2;" : "=r"(r) : "f"(hi), "f"(lo) : "memory"); return r;
}
__device__ __forceinline__ uint32_t add_bf2(uint32_t a, uint32_t b) { uint32_t r; asm("add.rn.bf16x2 %0, %1, %2;" : "=r"(r) : "r"(a), "r"(b)); return r; }
__device__ __forceinline__ float bf_lo(uint32_t u) { return __uint_as_float(u << 16); }
__device__ __forceinline__ float bf_hi(uint32_t u) { return __uint_as_float(u & 0xffff0000u); }

__device__ __forceinline__ uint64_t d128(uint32_t lo) { uint64_t d; asm("mov.b64 %0, {%1, 0x40000040};" : "=l"(d) : "r"(lo)); return d; }
__device__ __forceinline__ uint64_t d64(uint32_t lo) { uint64_t d; asm("mov.b64 %0, {%1, 0x80000020};" : "=l"(d) : "r"(lo)); return d; }
template<int O,int TB,int ACC,int NN> __device__ __forceinline__ void mma_ss64(float (&d)[NN], uint64_t da, uint64_t db, int sd = 0){
  if constexpr (ACC == 1) asm volatile("wgmma.mma_async.sync.aligned.m64n64k16.f32.bf16.bf16 {%0,%1,%2,%3,%4,%5,%6,%7,%8,%9,%10,%11,%12,%13,%14,%15,%16,%17,%18,%19,%20,%21,%22,%23,%24,%25,%26,%27,%28,%29,%30,%31}, %32, %33, 1, 1, 1, %35, %34;"
   : "+f"(d[O+0]), "+f"(d[O+1]), "+f"(d[O+2]), "+f"(d[O+3]), "+f"(d[O+4]), "+f"(d[O+5]), "+f"(d[O+6]), "+f"(d[O+7]), "+f"(d[O+8]), "+f"(d[O+9]), "+f"(d[O+10]), "+f"(d[O+11]), "+f"(d[O+12]), "+f"(d[O+13]), "+f"(d[O+14]), "+f"(d[O+15]), "+f"(d[O+16]), "+f"(d[O+17]), "+f"(d[O+18]), "+f"(d[O+19]), "+f"(d[O+20]), "+f"(d[O+21]), "+f"(d[O+22]), "+f"(d[O+23]), "+f"(d[O+24]), "+f"(d[O+25]), "+f"(d[O+26]), "+f"(d[O+27]), "+f"(d[O+28]), "+f"(d[O+29]), "+f"(d[O+30]), "+f"(d[O+31])
   : "l"(da), "l"(db), "n"(TB & 1), "n"(TB >> 1));
  else if constexpr (ACC == 0) asm volatile("wgmma.mma_async.sync.aligned.m64n64k16.f32.bf16.bf16 {%0,%1,%2,%3,%4,%5,%6,%7,%8,%9,%10,%11,%12,%13,%14,%15,%16,%17,%18,%19,%20,%21,%22,%23,%24,%25,%26,%27,%28,%29,%30,%31}, %32, %33, 0, 1, 1, %35, %34;"
   : "=f"(d[O+0]), "=f"(d[O+1]), "=f"(d[O+2]), "=f"(d[O+3]), "=f"(d[O+4]), "=f"(d[O+5]), "=f"(d[O+6]), "=f"(d[O+7]), "=f"(d[O+8]), "=f"(d[O+9]), "=f"(d[O+10]), "=f"(d[O+11]), "=f"(d[O+12]), "=f"(d[O+13]), "=f"(d[O+14]), "=f"(d[O+15]), "=f"(d[O+16]), "=f"(d[O+17]), "=f"(d[O+18]), "=f"(d[O+19]), "=f"(d[O+20]), "=f"(d[O+21]), "=f"(d[O+22]), "=f"(d[O+23]), "=f"(d[O+24]), "=f"(d[O+25]), "=f"(d[O+26]), "=f"(d[O+27]), "=f"(d[O+28]), "=f"(d[O+29]), "=f"(d[O+30]), "=f"(d[O+31])
   : "l"(da), "l"(db), "n"(TB & 1), "n"(TB >> 1));
  else asm volatile("{\n.reg .pred p;\nsetp.ne.b32 p, %36, 0;\nwgmma.mma_async.sync.aligned.m64n64k16.f32.bf16.bf16 {%0,%1,%2,%3,%4,%5,%6,%7,%8,%9,%10,%11,%12,%13,%14,%15,%16,%17,%18,%19,%20,%21,%22,%23,%24,%25,%26,%27,%28,%29,%30,%31}, %32, %33, p, 1, 1, %35, %34;\n}"
   : "+f"(d[O+0]), "+f"(d[O+1]), "+f"(d[O+2]), "+f"(d[O+3]), "+f"(d[O+4]), "+f"(d[O+5]), "+f"(d[O+6]), "+f"(d[O+7]), "+f"(d[O+8]), "+f"(d[O+9]), "+f"(d[O+10]), "+f"(d[O+11]), "+f"(d[O+12]), "+f"(d[O+13]), "+f"(d[O+14]), "+f"(d[O+15]), "+f"(d[O+16]), "+f"(d[O+17]), "+f"(d[O+18]), "+f"(d[O+19]), "+f"(d[O+20]), "+f"(d[O+21]), "+f"(d[O+22]), "+f"(d[O+23]), "+f"(d[O+24]), "+f"(d[O+25]), "+f"(d[O+26]), "+f"(d[O+27]), "+f"(d[O+28]), "+f"(d[O+29]), "+f"(d[O+30]), "+f"(d[O+31])
   : "l"(da), "l"(db), "n"(TB & 1), "n"(TB >> 1), "r"(sd));
}
template<int O,int TB,int ACC,int NN> __device__ __forceinline__ void mma_rs64(float (&d)[NN], uint32_t a0, uint32_t a1, uint32_t a2, uint32_t a3, uint64_t db, int sd = 0){
  if constexpr (ACC == 1) asm volatile("wgmma.mma_async.sync.aligned.m64n64k16.f32.bf16.bf16 {%0,%1,%2,%3,%4,%5,%6,%7,%8,%9,%10,%11,%12,%13,%14,%15,%16,%17,%18,%19,%20,%21,%22,%23,%24,%25,%26,%27,%28,%29,%30,%31}, {%32,%33,%34,%35}, %36, 1, 1, 1, %37;"
   : "+f"(d[O+0]), "+f"(d[O+1]), "+f"(d[O+2]), "+f"(d[O+3]), "+f"(d[O+4]), "+f"(d[O+5]), "+f"(d[O+6]), "+f"(d[O+7]), "+f"(d[O+8]), "+f"(d[O+9]), "+f"(d[O+10]), "+f"(d[O+11]), "+f"(d[O+12]), "+f"(d[O+13]), "+f"(d[O+14]), "+f"(d[O+15]), "+f"(d[O+16]), "+f"(d[O+17]), "+f"(d[O+18]), "+f"(d[O+19]), "+f"(d[O+20]), "+f"(d[O+21]), "+f"(d[O+22]), "+f"(d[O+23]), "+f"(d[O+24]), "+f"(d[O+25]), "+f"(d[O+26]), "+f"(d[O+27]), "+f"(d[O+28]), "+f"(d[O+29]), "+f"(d[O+30]), "+f"(d[O+31])
   : "r"(a0), "r"(a1), "r"(a2), "r"(a3), "l"(db), "n"(TB));
  else if constexpr (ACC == 0) asm volatile("wgmma.mma_async.sync.aligned.m64n64k16.f32.bf16.bf16 {%0,%1,%2,%3,%4,%5,%6,%7,%8,%9,%10,%11,%12,%13,%14,%15,%16,%17,%18,%19,%20,%21,%22,%23,%24,%25,%26,%27,%28,%29,%30,%31}, {%32,%33,%34,%35}, %36, 0, 1, 1, %37;"
   : "=f"(d[O+0]), "=f"(d[O+1]), "=f"(d[O+2]), "=f"(d[O+3]), "=f"(d[O+4]), "=f"(d[O+5]), "=f"(d[O+6]), "=f"(d[O+7]), "=f"(d[O+8]), "=f"(d[O+9]), "=f"(d[O+10]), "=f"(d[O+11]), "=f"(d[O+12]), "=f"(d[O+13]), "=f"(d[O+14]), "=f"(d[O+15]), "=f"(d[O+16]), "=f"(d[O+17]), "=f"(d[O+18]), "=f"(d[O+19]), "=f"(d[O+20]), "=f"(d[O+21]), "=f"(d[O+22]), "=f"(d[O+23]), "=f"(d[O+24]), "=f"(d[O+25]), "=f"(d[O+26]), "=f"(d[O+27]), "=f"(d[O+28]), "=f"(d[O+29]), "=f"(d[O+30]), "=f"(d[O+31])
   : "r"(a0), "r"(a1), "r"(a2), "r"(a3), "l"(db), "n"(TB));
  else asm volatile("{\n.reg .pred p;\nsetp.ne.b32 p, %38, 0;\nwgmma.mma_async.sync.aligned.m64n64k16.f32.bf16.bf16 {%0,%1,%2,%3,%4,%5,%6,%7,%8,%9,%10,%11,%12,%13,%14,%15,%16,%17,%18,%19,%20,%21,%22,%23,%24,%25,%26,%27,%28,%29,%30,%31}, {%32,%33,%34,%35}, %36, p, 1, 1, %37;\n}"
   : "+f"(d[O+0]), "+f"(d[O+1]), "+f"(d[O+2]), "+f"(d[O+3]), "+f"(d[O+4]), "+f"(d[O+5]), "+f"(d[O+6]), "+f"(d[O+7]), "+f"(d[O+8]), "+f"(d[O+9]), "+f"(d[O+10]), "+f"(d[O+11]), "+f"(d[O+12]), "+f"(d[O+13]), "+f"(d[O+14]), "+f"(d[O+15]), "+f"(d[O+16]), "+f"(d[O+17]), "+f"(d[O+18]), "+f"(d[O+19]), "+f"(d[O+20]), "+f"(d[O+21]), "+f"(d[O+22]), "+f"(d[O+23]), "+f"(d[O+24]), "+f"(d[O+25]), "+f"(d[O+26]), "+f"(d[O+27]), "+f"(d[O+28]), "+f"(d[O+29]), "+f"(d[O+30]), "+f"(d[O+31])
   : "r"(a0), "r"(a1), "r"(a2), "r"(a3), "l"(db), "n"(TB), "r"(sd));
}
template<int O,int TB,int ACC,int NN> __device__ __forceinline__ void mma_ss128(float (&d)[NN], uint64_t da, uint64_t db, int sd = 0){
  if constexpr (ACC == 1) asm volatile("wgmma.mma_async.sync.aligned.m64n128k16.f32.bf16.bf16 {%0,%1,%2,%3,%4,%5,%6,%7,%8,%9,%10,%11,%12,%13,%14,%15,%16,%17,%18,%19,%20,%21,%22,%23,%24,%25,%26,%27,%28,%29,%30,%31,%32,%33,%34,%35,%36,%37,%38,%39,%40,%41,%42,%43,%44,%45,%46,%47,%48,%49,%50,%51,%52,%53,%54,%55,%56,%57,%58,%59,%60,%61,%62,%63}, %64, %65, 1, 1, 1, %67, %66;"
   : "+f"(d[O+0]), "+f"(d[O+1]), "+f"(d[O+2]), "+f"(d[O+3]), "+f"(d[O+4]), "+f"(d[O+5]), "+f"(d[O+6]), "+f"(d[O+7]), "+f"(d[O+8]), "+f"(d[O+9]), "+f"(d[O+10]), "+f"(d[O+11]), "+f"(d[O+12]), "+f"(d[O+13]), "+f"(d[O+14]), "+f"(d[O+15]), "+f"(d[O+16]), "+f"(d[O+17]), "+f"(d[O+18]), "+f"(d[O+19]), "+f"(d[O+20]), "+f"(d[O+21]), "+f"(d[O+22]), "+f"(d[O+23]), "+f"(d[O+24]), "+f"(d[O+25]), "+f"(d[O+26]), "+f"(d[O+27]), "+f"(d[O+28]), "+f"(d[O+29]), "+f"(d[O+30]), "+f"(d[O+31]), "+f"(d[O+32]), "+f"(d[O+33]), "+f"(d[O+34]), "+f"(d[O+35]), "+f"(d[O+36]), "+f"(d[O+37]), "+f"(d[O+38]), "+f"(d[O+39]), "+f"(d[O+40]), "+f"(d[O+41]), "+f"(d[O+42]), "+f"(d[O+43]), "+f"(d[O+44]), "+f"(d[O+45]), "+f"(d[O+46]), "+f"(d[O+47]), "+f"(d[O+48]), "+f"(d[O+49]), "+f"(d[O+50]), "+f"(d[O+51]), "+f"(d[O+52]), "+f"(d[O+53]), "+f"(d[O+54]), "+f"(d[O+55]), "+f"(d[O+56]), "+f"(d[O+57]), "+f"(d[O+58]), "+f"(d[O+59]), "+f"(d[O+60]), "+f"(d[O+61]), "+f"(d[O+62]), "+f"(d[O+63])
   : "l"(da), "l"(db), "n"(TB & 1), "n"(TB >> 1));
  else if constexpr (ACC == 0) asm volatile("wgmma.mma_async.sync.aligned.m64n128k16.f32.bf16.bf16 {%0,%1,%2,%3,%4,%5,%6,%7,%8,%9,%10,%11,%12,%13,%14,%15,%16,%17,%18,%19,%20,%21,%22,%23,%24,%25,%26,%27,%28,%29,%30,%31,%32,%33,%34,%35,%36,%37,%38,%39,%40,%41,%42,%43,%44,%45,%46,%47,%48,%49,%50,%51,%52,%53,%54,%55,%56,%57,%58,%59,%60,%61,%62,%63}, %64, %65, 0, 1, 1, %67, %66;"
   : "=f"(d[O+0]), "=f"(d[O+1]), "=f"(d[O+2]), "=f"(d[O+3]), "=f"(d[O+4]), "=f"(d[O+5]), "=f"(d[O+6]), "=f"(d[O+7]), "=f"(d[O+8]), "=f"(d[O+9]), "=f"(d[O+10]), "=f"(d[O+11]), "=f"(d[O+12]), "=f"(d[O+13]), "=f"(d[O+14]), "=f"(d[O+15]), "=f"(d[O+16]), "=f"(d[O+17]), "=f"(d[O+18]), "=f"(d[O+19]), "=f"(d[O+20]), "=f"(d[O+21]), "=f"(d[O+22]), "=f"(d[O+23]), "=f"(d[O+24]), "=f"(d[O+25]), "=f"(d[O+26]), "=f"(d[O+27]), "=f"(d[O+28]), "=f"(d[O+29]), "=f"(d[O+30]), "=f"(d[O+31]), "=f"(d[O+32]), "=f"(d[O+33]), "=f"(d[O+34]), "=f"(d[O+35]), "=f"(d[O+36]), "=f"(d[O+37]), "=f"(d[O+38]), "=f"(d[O+39]), "=f"(d[O+40]), "=f"(d[O+41]), "=f"(d[O+42]), "=f"(d[O+43]), "=f"(d[O+44]), "=f"(d[O+45]), "=f"(d[O+46]), "=f"(d[O+47]), "=f"(d[O+48]), "=f"(d[O+49]), "=f"(d[O+50]), "=f"(d[O+51]), "=f"(d[O+52]), "=f"(d[O+53]), "=f"(d[O+54]), "=f"(d[O+55]), "=f"(d[O+56]), "=f"(d[O+57]), "=f"(d[O+58]), "=f"(d[O+59]), "=f"(d[O+60]), "=f"(d[O+61]), "=f"(d[O+62]), "=f"(d[O+63])
   : "l"(da), "l"(db), "n"(TB & 1), "n"(TB >> 1));
  else asm volatile("{\n.reg .pred p;\nsetp.ne.b32 p, %68, 0;\nwgmma.mma_async.sync.aligned.m64n128k16.f32.bf16.bf16 {%0,%1,%2,%3,%4,%5,%6,%7,%8,%9,%10,%11,%12,%13,%14,%15,%16,%17,%18,%19,%20,%21,%22,%23,%24,%25,%26,%27,%28,%29,%30,%31,%32,%33,%34,%35,%36,%37,%38,%39,%40,%41,%42,%43,%44,%45,%46,%47,%48,%49,%50,%51,%52,%53,%54,%55,%56,%57,%58,%59,%60,%61,%62,%63}, %64, %65, p, 1, 1, %67, %66;\n}"
   : "+f"(d[O+0]), "+f"(d[O+1]), "+f"(d[O+2]), "+f"(d[O+3]), "+f"(d[O+4]), "+f"(d[O+5]), "+f"(d[O+6]), "+f"(d[O+7]), "+f"(d[O+8]), "+f"(d[O+9]), "+f"(d[O+10]), "+f"(d[O+11]), "+f"(d[O+12]), "+f"(d[O+13]), "+f"(d[O+14]), "+f"(d[O+15]), "+f"(d[O+16]), "+f"(d[O+17]), "+f"(d[O+18]), "+f"(d[O+19]), "+f"(d[O+20]), "+f"(d[O+21]), "+f"(d[O+22]), "+f"(d[O+23]), "+f"(d[O+24]), "+f"(d[O+25]), "+f"(d[O+26]), "+f"(d[O+27]), "+f"(d[O+28]), "+f"(d[O+29]), "+f"(d[O+30]), "+f"(d[O+31]), "+f"(d[O+32]), "+f"(d[O+33]), "+f"(d[O+34]), "+f"(d[O+35]), "+f"(d[O+36]), "+f"(d[O+37]), "+f"(d[O+38]), "+f"(d[O+39]), "+f"(d[O+40]), "+f"(d[O+41]), "+f"(d[O+42]), "+f"(d[O+43]), "+f"(d[O+44]), "+f"(d[O+45]), "+f"(d[O+46]), "+f"(d[O+47]), "+f"(d[O+48]), "+f"(d[O+49]), "+f"(d[O+50]), "+f"(d[O+51]), "+f"(d[O+52]), "+f"(d[O+53]), "+f"(d[O+54]), "+f"(d[O+55]), "+f"(d[O+56]), "+f"(d[O+57]), "+f"(d[O+58]), "+f"(d[O+59]), "+f"(d[O+60]), "+f"(d[O+61]), "+f"(d[O+62]), "+f"(d[O+63])
   : "l"(da), "l"(db), "n"(TB & 1), "n"(TB >> 1), "r"(sd));
}
template<int O,int TB,int ACC,int NN> __device__ __forceinline__ void mma_rs128(float (&d)[NN], uint32_t a0, uint32_t a1, uint32_t a2, uint32_t a3, uint64_t db, int sd = 0){
  if constexpr (ACC == 1) asm volatile("wgmma.mma_async.sync.aligned.m64n128k16.f32.bf16.bf16 {%0,%1,%2,%3,%4,%5,%6,%7,%8,%9,%10,%11,%12,%13,%14,%15,%16,%17,%18,%19,%20,%21,%22,%23,%24,%25,%26,%27,%28,%29,%30,%31,%32,%33,%34,%35,%36,%37,%38,%39,%40,%41,%42,%43,%44,%45,%46,%47,%48,%49,%50,%51,%52,%53,%54,%55,%56,%57,%58,%59,%60,%61,%62,%63}, {%64,%65,%66,%67}, %68, 1, 1, 1, %69;"
   : "+f"(d[O+0]), "+f"(d[O+1]), "+f"(d[O+2]), "+f"(d[O+3]), "+f"(d[O+4]), "+f"(d[O+5]), "+f"(d[O+6]), "+f"(d[O+7]), "+f"(d[O+8]), "+f"(d[O+9]), "+f"(d[O+10]), "+f"(d[O+11]), "+f"(d[O+12]), "+f"(d[O+13]), "+f"(d[O+14]), "+f"(d[O+15]), "+f"(d[O+16]), "+f"(d[O+17]), "+f"(d[O+18]), "+f"(d[O+19]), "+f"(d[O+20]), "+f"(d[O+21]), "+f"(d[O+22]), "+f"(d[O+23]), "+f"(d[O+24]), "+f"(d[O+25]), "+f"(d[O+26]), "+f"(d[O+27]), "+f"(d[O+28]), "+f"(d[O+29]), "+f"(d[O+30]), "+f"(d[O+31]), "+f"(d[O+32]), "+f"(d[O+33]), "+f"(d[O+34]), "+f"(d[O+35]), "+f"(d[O+36]), "+f"(d[O+37]), "+f"(d[O+38]), "+f"(d[O+39]), "+f"(d[O+40]), "+f"(d[O+41]), "+f"(d[O+42]), "+f"(d[O+43]), "+f"(d[O+44]), "+f"(d[O+45]), "+f"(d[O+46]), "+f"(d[O+47]), "+f"(d[O+48]), "+f"(d[O+49]), "+f"(d[O+50]), "+f"(d[O+51]), "+f"(d[O+52]), "+f"(d[O+53]), "+f"(d[O+54]), "+f"(d[O+55]), "+f"(d[O+56]), "+f"(d[O+57]), "+f"(d[O+58]), "+f"(d[O+59]), "+f"(d[O+60]), "+f"(d[O+61]), "+f"(d[O+62]), "+f"(d[O+63])
   : "r"(a0), "r"(a1), "r"(a2), "r"(a3), "l"(db), "n"(TB));
  else if constexpr (ACC == 0) asm volatile("wgmma.mma_async.sync.aligned.m64n128k16.f32.bf16.bf16 {%0,%1,%2,%3,%4,%5,%6,%7,%8,%9,%10,%11,%12,%13,%14,%15,%16,%17,%18,%19,%20,%21,%22,%23,%24,%25,%26,%27,%28,%29,%30,%31,%32,%33,%34,%35,%36,%37,%38,%39,%40,%41,%42,%43,%44,%45,%46,%47,%48,%49,%50,%51,%52,%53,%54,%55,%56,%57,%58,%59,%60,%61,%62,%63}, {%64,%65,%66,%67}, %68, 0, 1, 1, %69;"
   : "=f"(d[O+0]), "=f"(d[O+1]), "=f"(d[O+2]), "=f"(d[O+3]), "=f"(d[O+4]), "=f"(d[O+5]), "=f"(d[O+6]), "=f"(d[O+7]), "=f"(d[O+8]), "=f"(d[O+9]), "=f"(d[O+10]), "=f"(d[O+11]), "=f"(d[O+12]), "=f"(d[O+13]), "=f"(d[O+14]), "=f"(d[O+15]), "=f"(d[O+16]), "=f"(d[O+17]), "=f"(d[O+18]), "=f"(d[O+19]), "=f"(d[O+20]), "=f"(d[O+21]), "=f"(d[O+22]), "=f"(d[O+23]), "=f"(d[O+24]), "=f"(d[O+25]), "=f"(d[O+26]), "=f"(d[O+27]), "=f"(d[O+28]), "=f"(d[O+29]), "=f"(d[O+30]), "=f"(d[O+31]), "=f"(d[O+32]), "=f"(d[O+33]), "=f"(d[O+34]), "=f"(d[O+35]), "=f"(d[O+36]), "=f"(d[O+37]), "=f"(d[O+38]), "=f"(d[O+39]), "=f"(d[O+40]), "=f"(d[O+41]), "=f"(d[O+42]), "=f"(d[O+43]), "=f"(d[O+44]), "=f"(d[O+45]), "=f"(d[O+46]), "=f"(d[O+47]), "=f"(d[O+48]), "=f"(d[O+49]), "=f"(d[O+50]), "=f"(d[O+51]), "=f"(d[O+52]), "=f"(d[O+53]), "=f"(d[O+54]), "=f"(d[O+55]), "=f"(d[O+56]), "=f"(d[O+57]), "=f"(d[O+58]), "=f"(d[O+59]), "=f"(d[O+60]), "=f"(d[O+61]), "=f"(d[O+62]), "=f"(d[O+63])
   : "r"(a0), "r"(a1), "r"(a2), "r"(a3), "l"(db), "n"(TB));
  else asm volatile("{\n.reg .pred p;\nsetp.ne.b32 p, %70, 0;\nwgmma.mma_async.sync.aligned.m64n128k16.f32.bf16.bf16 {%0,%1,%2,%3,%4,%5,%6,%7,%8,%9,%10,%11,%12,%13,%14,%15,%16,%17,%18,%19,%20,%21,%22,%23,%24,%25,%26,%27,%28,%29,%30,%31,%32,%33,%34,%35,%36,%37,%38,%39,%40,%41,%42,%43,%44,%45,%46,%47,%48,%49,%50,%51,%52,%53,%54,%55,%56,%57,%58,%59,%60,%61,%62,%63}, {%64,%65,%66,%67}, %68, p, 1, 1, %69;\n}"
   : "+f"(d[O+0]), "+f"(d[O+1]), "+f"(d[O+2]), "+f"(d[O+3]), "+f"(d[O+4]), "+f"(d[O+5]), "+f"(d[O+6]), "+f"(d[O+7]), "+f"(d[O+8]), "+f"(d[O+9]), "+f"(d[O+10]), "+f"(d[O+11]), "+f"(d[O+12]), "+f"(d[O+13]), "+f"(d[O+14]), "+f"(d[O+15]), "+f"(d[O+16]), "+f"(d[O+17]), "+f"(d[O+18]), "+f"(d[O+19]), "+f"(d[O+20]), "+f"(d[O+21]), "+f"(d[O+22]), "+f"(d[O+23]), "+f"(d[O+24]), "+f"(d[O+25]), "+f"(d[O+26]), "+f"(d[O+27]), "+f"(d[O+28]), "+f"(d[O+29]), "+f"(d[O+30]), "+f"(d[O+31]), "+f"(d[O+32]), "+f"(d[O+33]), "+f"(d[O+34]), "+f"(d[O+35]), "+f"(d[O+36]), "+f"(d[O+37]), "+f"(d[O+38]), "+f"(d[O+39]), "+f"(d[O+40]), "+f"(d[O+41]), "+f"(d[O+42]), "+f"(d[O+43]), "+f"(d[O+44]), "+f"(d[O+45]), "+f"(d[O+46]), "+f"(d[O+47]), "+f"(d[O+48]), "+f"(d[O+49]), "+f"(d[O+50]), "+f"(d[O+51]), "+f"(d[O+52]), "+f"(d[O+53]), "+f"(d[O+54]), "+f"(d[O+55]), "+f"(d[O+56]), "+f"(d[O+57]), "+f"(d[O+58]), "+f"(d[O+59]), "+f"(d[O+60]), "+f"(d[O+61]), "+f"(d[O+62]), "+f"(d[O+63])
   : "r"(a0), "r"(a1), "r"(a2), "r"(a3), "l"(db), "n"(TB), "r"(sd));
}

#define NEARLY 0
#define XAHEAD 3
#define HEADN 6
#define WBATCH 1
#define WB 8
#define WSLEEP 20
#define XSPREAD 4
#define NOSEND 0
#define MSPLIT 2
#define PFALL 1
#define L2PF 0
#define STAG 0
#define EPF 2
#define XNB 2
#define FNB 0
#define GNB 0
#define TH 4
#define PF0 4
#define FSPLIT 1
#define MGLU 1
#define SPC 2
#define TL 14
#define GKB 4
#define T0A 7
#define T0B 11
#define TGATE 1
#define ZLATE 0
#define EARLYADD 0
#define OA 3
#define OB 11
#define EB 8
#define SPACE 100
#define WPF 1
#define WAFTER 7
#define WPACE 0
#define GATE_AT 4
#define TPACE 40
#define PFMODE 0
#define MAPMODE 1
template <int V> struct IC { static constexpr int value = V; };
struct Maps { CUtensorMap x, ft, g64, u64, e, wr, wi, xs, ts, t, g32, u32, d224, fg; };

constexpr int NCTA = 130;
constexpr int U = 16384;
constexpr int TB = 36864;
constexpr int OFF_RING = 8 * U, OFF_Z = 12 * U, OFF_XB = 12 * U, OFF_T = 13 * U, OFF_D = OFF_T;
constexpr int OFF_BAR = 14 * U, OFF_SP = OFF_BAR + 512, OFF_G = OFF_SP + 1024 + 128;
constexpr int SMEM_BYTES = OFF_G + 512;
constexpr int B_FX = 0, B_FA = 8, B_FT = 12, B_Z = 16, B_W = 24, B_HX = 25, B_TL = 26, B_HP = 27, B_WR = 31, B_E0 = 35;
constexpr int B_EA = 36, B_ET = 40, B_PZ = 44, B_RDY = 46, B_FE = 47;
constexpr int B_T = 51, B_XS = 52, B_G = 54, B_RD0 = 55, NBAR = 56;
__host__ __device__ constexpr int rslot(int n) { return n & 3; }
__host__ __device__ constexpr int rpar(int n) { return (n >> 2) & 1; }

__global__ void __cluster_dims__(2, 1, 1) __launch_bounds__(512, 1)
fused_kernel(Work* __restrict__ ws, const uint16_t* __restrict__ dtab, const __nv_bfloat16* __restrict__ w_r, const __nv_bfloat16* __restrict__ w_i,
             const __nv_bfloat16* __restrict__ gate_w, const __nv_bfloat16* __restrict__ x, __nv_bfloat16* __restrict__ out,
             const __grid_constant__ Maps maps) {
  extern __shared__ __align__(1024) uint8_t smem[];
  if (threadIdx.x < 32 && elect_one()) {
#pragma unroll
    for (int i = 0; i < PF0; i++) asm volatile("prefetch.tensormap [%0];" ::"l"((const char*)&maps + i * 128) : "memory");
  }
  const uint32_t sb = smem_u32(smem);
  const uint32_t bars = sb + OFF_BAR;
  const int tid = threadIdx.x, lane = tid & 31;
  const int warp = __shfl_sync(0xffffffffu, tid >> 5, 0);
  const bool helper = blockIdx.x >= 128;
  const int cl = (blockIdx.x >> 1) & 63, rank = blockIdx.x & 1;
  const int q4 = (cl & 1) | ((cl >> 2) & 2), rb = ((cl >> 1) & 3) | ((cl >> 4) << 2);
  const int j = 2 * q4 + rank;
  const int f_full = 448 * q4 + (rank ? 256 : 0);
  const int f_half = 448 * q4 + (rank ? 224 : 192);

  if (tid == 64) { PROF_EV(0); PROF_CK(40); }
  if (warp < 8) {
    if (!helper && tid < 32) {
      const int r = 16 * j + (tid & 15);
      asm volatile("prefetch.global.L2 [%0];" ::"l"(x + (size_t)(2 * rb + (r >> 6) + 32 * (r & 63)) * 512 + 64 * (tid >> 4)));
    }
    asm volatile("barrier.cluster.arrive.relaxed.aligned;" ::: "memory");
    asm volatile("setmaxnreg.inc.sync.aligned.u32 192;");
    if (!helper) {
      const int wg = warp >> 2, w = warp & 3, g = lane >> 2;
      const bool elect = (tid & 127) == 0;
      float cX[32], cA[64], cB[64], cC[64], ci[64], ct[64];
      const int zero = blockIdx.x >> 16;
      uint32_t h[56], yf[16];
      const uint32_t d0 = (sb & 0x3FFFF) >> 4;
      const uint32_t dK = d0 | (1u << 16), dN = d0 | (512u << 16);
      const uint32_t dX = dK + wg * 512;
      constexpr uint32_t RING = OFF_RING >> 4;
      auto waitA = [&](int n) { mbar_wait(bars + 8 * (B_FA + rslot(n)), rpar(n)); };
      auto freeA = [&](int n) { mbar_arrive_if(elect, bars + 8 * (B_EA + rslot(n))); };
      auto nop = [] {};

      asm volatile("bar.sync 0, 384;" ::: "memory");
#pragma unroll 1
      for (int i = 0; i < 4; i++) {
        const uint64_t dx = d128(dX + i * 2048), df = d128(dK + (OFF_XB >> 4) + (i & 1) * 1024);
        mbar_wait(bars + 8 * (B_FX + 2 * i), 0);
        wg_fence();
        mma_ss64<0, 0, 2>(cX, df, dx, i);
        mma_ss64<0, 0, 1>(cX, df + 2, dx + 2);
        wg_commit(); wg_wait<1>();
        mbar_arrive_if(elect && i, bars + 8 * (B_EA + rslot(i - 1)));
        mma_ss64<0, 0, 1>(cX, df + 4, dx + 4);
        mma_ss64<0, 0, 1>(cX, df + 6, dx + 6);
        if (i == 0 && tid == 0) PROF_EV(1);
        mbar_wait(bars + 8 * (B_FX + 2 * i + 1), 0);
        wg_fence();
#pragma unroll
        for (int k = 0; k < 4; k++) mma_ss64<0, 0, 1>(cX, df + (512 + k * 2), dx + (1024 + k * 2));
        wg_commit();
        waitA(i);
        wg_fence();
        const uint64_t da = d128(dX + i * 1024), db = d128(dN + RING + i * 1024);
        mma_ss128<0, 1, 2>(cA, da, db, i);
        wg_commit(); wg_wait<1>();
        mbar_arrive_if(elect, bars + 8 * (B_FE + i));
#pragma unroll
        for (int k = 1; k < 4; k++) mma_ss128<0, 1, 1>(cA, da + k * 2, db + k * 128);
        wg_commit();
      }
      fence_regs<0, 32>(cX);
#pragma unroll
      for (int e = 0; e < 16; e++) yf[e] = pack_pin(cX[2 * e], cX[2 * e + 1]);
      if (tid == 0) { PROF_EV(2); PROF_CK(42); }
      {
        waitA(4); mbar_wait(bars + 8 * B_E0, 0);
        const uint64_t de = d128(dN + (wg ? RING : OFF_XB >> 4));
        wg_fence();
        mma_rs128<0, 1, 0>(cB, yf[0], yf[1], yf[2], yf[3], de);
        wg_commit();
        wg_wait<1>();
        freeA(3);
#pragma unroll
        for (int k = 1; k < 4; k++) mma_rs128<0, 1, 1>(cB, yf[4 * k], yf[4 * k + 1], yf[4 * k + 2], yf[4 * k + 3], de + k * 128);
        wg_commit();
      }
      bool rel = false;
      auto acquire = [&](int n) {
        rel = elect;
        if (!mbar_try(bars + 8 * (B_FA + rslot(n)), rpar(n))) { wg_wait<0>(); freeA(n - 1); rel = false; waitA(n); }
      };
      auto freeP = [&](int n) { mbar_arrive_if(rel, bars + 8 * (B_EA + rslot(n - 1))); };
      auto ffn_step = [&](auto first, auto split, float (&acc)[64], int n, int kb, auto done, auto work) {
        constexpr int SPLIT = decltype(split)::value;
        acquire(n);
        wg_fence();
        const uint64_t dx = d128(dX + kb * 1024), db = d128(dN + RING + rslot(n) * 1024);
        mma_ss128<0, 1, decltype(first)::value>(acc, dx, db, kb);
#pragma unroll
        for (int k = 1; k < SPLIT; k++) mma_ss128<0, 1, 1>(acc, dx + k * 2, db + k * 128);
        wg_commit();
        work();
        wg_wait<1>();
        freeP(n);
        done();
        if (SPLIT < 4) {
          wg_fence();
#pragma unroll
          for (int k = SPLIT; k < 4; k++) mma_ss128<0, 1, 1>(acc, dx + k * 2, db + k * 128);
          wg_commit();
        }
      };
      {
        const int s0 = 2 * rb + wg, kr = 2 * ((s0 & 1) | ((s0 & 4) >> 1));
        const int m = lane >> 3, r = lane & 7;
        const uint32_t a0 = sb + OFF_XB + wg * 8192 + ((2 * (m >> 1) + (r >> 2)) * 2 + (w & 1)) * 256 + (m & 1) * 128 + (((2 * (r & 3) + ((w >> 1) ^ (r >> 2))) ^ (kr + (m & 1))) << 4);
        ffn_step(IC<1>(), IC<4>(), cA, 5, 4, [&] { fence_regs<0, 64>(cB); }, nop);
        asm volatile("bar.sync 5, 256;" ::: "memory");
        auto stage = [&](int i) {
          stsm4t(a0 + i * 2048, pack_bf16(cB[8 * i] - cB[34 + 8 * i], cB[8 * i + 1] - cB[35 + 8 * i]),
                 pack_bf16(cB[32 + 8 * i] + cB[8 * i + 2], cB[33 + 8 * i] + cB[8 * i + 3]),
                 pack_bf16(cB[8 * i + 4] - cB[38 + 8 * i], cB[8 * i + 5] - cB[39 + 8 * i]),
                 pack_bf16(cB[36 + 8 * i] + cB[8 * i + 6], cB[37 + 8 * i] + cB[8 * i + 7]));
          if (j == 0 && w == 0) {
            const uint32_t a1 = r ? sb + OFF_SP + 1024 : sb + OFF_SP + wg * 512 + (m & 1) * 256 + (m >> 1) * 128;
#pragma unroll
            for (int n = 2 * i; n < 2 * i + 2; n++)
              asm volatile("stmatrix.sync.aligned.m8n8.x4.shared.b16 [%0], {%1,%2,%3,%4};" ::"r"(a1 + ((n ^ (kr + (m >> 1)) ^ r) << 4)),
                           "r"(pack_bf16(cB[4 * n], cB[4 * n + 1])), "r"(pack_bf16(cB[4 * n + 2], cB[4 * n + 3])),
                           "r"(pack_bf16(cB[32 + 4 * n], cB[33 + 4 * n])), "r"(pack_bf16(cB[34 + 4 * n], cB[35 + 4 * n])) : "memory");
          }
        };
        auto publish = [&] {
          asm volatile("fence.proxy.async.shared::cta;" ::: "memory");
          __syncwarp();
          mbar_arrive_if(lane == 0, bars + 8 * (B_XS + wg));
          if (tid == 0) PROF_EV(3);
        };
        stage(0);
        ffn_step(IC<1>(), IC<FSPLIT>(), cA, 6, 5, nop, nop);
        stage(1);
        ffn_step(IC<1>(), IC<FSPLIT>(), cA, 7, 6, nop, nop);
        stage(2);
        ffn_step(IC<1>(), IC<2>(), cA, 8, 7, [&] { stage(3); }, nop);
        publish();
      }
      uint32_t gb0 = 0, gb1 = 0;
      uint32_t ob[2] = {0, 0};
      auto glu = [&](auto& acc, int half, int ho, int i0, int i1) {
#pragma unroll
        for (int i = i0; i < i1; i++)
          asm volatile("{\n.reg .b32 a, b;\ncvt.rn.relu.bf16x2.f32 a, %2, %1;\ncvt.rn.bf16x2.f32 b, %4, %3;\nmul.rn.bf16x2 a, a, b;\nmul.rn.bf16x2 %0, a, %5;\n}"
                       : "=r"(h[ho + i]) : "f"(acc[2 * i]), "f"(acc[2 * i + 1]), "f"(acc[half + 2 * i]), "f"(acc[half + 1 + 2 * i]), "r"(ob[i & 1]) : "memory");
      };
      ffn_step(IC<2>(), IC<1>(), cB, 9, zero, nop, nop);
#pragma unroll 1
      for (int kb = 1; kb < 8; kb++)
        ffn_step(IC<1>(), IC<FSPLIT>(), cB, 9 + kb, kb, nop, [&] {
          if (kb == GKB) {
            mbar_wait(bars + 8 * B_G, 0);
            asm volatile("ld.shared.u32 %0, [%2];\nld.shared.u32 %1, [%2+32];" : "=r"(gb0), "=r"(gb1) : "r"(sb + OFF_G + (wg * 64 + w * 16 + g) * 4) : "memory");
          } else if (kb == 5 + 2 * wg) {
            ob[0] = pack_bf16(1.0f - bf_hi(gb0), 1.0f - bf_hi(gb0)); ob[1] = pack_bf16(1.0f - bf_hi(gb1), 1.0f - bf_hi(gb1));
            glu(cA, 32, 0, 0, 16);
          }
        });
      const uint32_t tag = gb0 & 1;
      const float g0 = bf_hi(gb0), g1 = bf_hi(gb1);
      if (tid == 0) { PROF_EV(4); PROF_CK(43); }
      auto m_step = [&](auto first, int i) {
        acquire(17 + i);
        wg_fence();
        const uint64_t dx = d128(dX + i * 2048), dm = d64(dN + RING + rslot(17 + i) * 1024);
        mma_ss64<0, 1, decltype(first)::value>(ct, dx, dm);
#pragma unroll
        for (int k = 1; k < MSPLIT; k++) mma_ss64<0, 1, 1>(ct, dx + ((k >> 2) * 1024 + (k & 3) * 2), dm + k * 64);
        wg_commit();
        wg_wait<1>();
        freeP(17 + i);
        wg_fence();
#pragma unroll
        for (int k = MSPLIT; k < 8; k++) mma_ss64<0, 1, 1>(ct, dx + ((k >> 2) * 1024 + (k & 3) * 2), dm + k * 64);
        wg_commit();
      };
      m_step(IC<0>(), 0);
#pragma unroll 1
      for (int i = 1; i < 5; i++) {
        if (i == 1 + 2 * wg) glu(cB, 32, 16, 0, 16);
        if (i < 4) m_step(IC<1>(), i);
      }
      if (tid == 0) { PROF_EV(5); PROF_CK(44); }
      ffn_step(IC<0>(), IC<1>(), cC, 21, 0, nop, nop);
#pragma unroll 1
      for (int kb = 1; kb < 8; kb++)
        ffn_step(IC<1>(), IC<FSPLIT>(), cC, 21 + kb, kb, [&] { mbar_arrive_if(elect && !(kb & 1), bars + 8 * (B_ET + (kb >> 1) - 1)); }, [&] {
          if (kb == 1 + wg) glu(ct, 16, 48, 0, 8);
        });

      auto twait = [&](uint32_t bar, uint32_t par, int) { mbar_wait(bar, par); };
      const int fo = warp * 128 + lane;
      auto fetch = [&](uint4 (&pv)[4], int z) {
        twait(bars + 8 * (z == 2 ? B_Z + 4 : z < 4 ? B_Z + 2 * z + wg : z < 6 ? B_HP + z - 4 : B_HP + 2 + wg), 0, 8 + z);
        const uint8_t* src = smem + (z < 4 ? OFF_Z - z * U : z == 4 ? OFF_T : (z - 5) * U) + fo * 16;
#pragma unroll
        for (int i = 0; i < 4; i++) pv[i] = *(const uint4*)(src + i * 512);
      };
      const uint32_t peerZ = mapa(sb + OFF_Z + fo * 16, rank ^ 1), peerB = mapa(bars + 8 * (B_Z + wg), rank ^ 1);
      auto tile_mma = [&](auto off, int t, int k0, int k1, bool fresh = false) {
        constexpr int O = decltype(off)::value;
        const uint64_t db = d128(dN + (t & 3) * (TB >> 4)), dw = db + rank * 256, dm = db + (rank ? 0 : 1536);
#pragma unroll
        for (int k = k0; k < k1; k++) {
          if (k == 0 && O == 0) mma_rs64<O, 1, 2>(ct, h[0], h[1], h[2], h[3], dw, zero);
          else if (k < 14) mma_rs64<O, 1, 1>(ct, h[4 * k], h[4 * k + 1], h[4 * k + 2], h[4 * k + 3], k < 12 ? dw + k * 128 : dm + (k - 12) * 128);
          else if (k == 14 && fresh) mma_rs64<O, 1, 0>(ct, yf[0], yf[1], yf[2], yf[3], db + k * 128);
          else if (k == 14) mma_rs64<O, 1, 2>(ct, yf[0], yf[1], yf[2], yf[3], db + k * 128, zero);
          else mma_rs64<O, 1, 1>(ct, yf[4 * k - 56], yf[4 * k - 55], yf[4 * k - 54], yf[4 * k - 53], db + k * 128);
        }
      };
      uint4 pv[4];
      const uint32_t sgn = rank ? 0x80008000u : 0u;
      auto even_end = [&](int t, int k0, bool fresh) {
        wg_fence();
        tile_mma(IC<32>(), t, 14, 18, fresh);
        wg_commit();
        tile_mma(IC<0>(), t, k0, 14);
        wg_commit();
        wg_wait<1>();
        fence_regs<32, 32>(ct);
#pragma unroll
        for (int i = 0; i < 4; i++)
          pv[i] = make_uint4(pack_pin(ct[32 + 8 * i], ct[33 + 8 * i]) ^ sgn, pack_pin(ct[34 + 8 * i], ct[35 + 8 * i]) ^ sgn,
                             pack_pin(ct[36 + 8 * i], ct[37 + 8 * i]) ^ sgn, pack_pin(ct[38 + 8 * i], ct[39 + 8 * i]) ^ sgn);
      };
      auto to_owner = [&](int owner, int slot, int cnt) {
        uint4* dst = ws->part + (size_t)(owner * 4 + slot) * 1024 + fo;
#pragma unroll
        for (int i = 0; i < 4; i++)
          asm volatile("st.relaxed.gpu.global.v4.u32 [%0], {%1,%2,%3,%4};" ::"l"(dst + i * 32), "r"((pv[i].x & ~1u) | tag), "r"(pv[i].y), "r"(pv[i].z), "r"(pv[i].w) : "memory");
        hint_add_if(lane == 0, &ws->cntP[64 * owner + 8 * cnt]);
      };
      auto odd_head = [&](int t) {
        twait(bars + 8 * (B_FT + (t & 3)), t >> 2, t);
        wg_fence();
        tile_mma(IC<32>(), t, 0, OA);
        wg_commit();
        if (t < 4) twait(bars + 8 * (t == 1 ? B_RD0 : B_RDY), 0, 14 + t);
        wg_wait<1>();
        mbar_arrive_if(elect && t < 6, bars + 8 * (B_ET + t - 1));
        fence_regs<0, 32>(ct);
#pragma unroll
        for (int i = 0; i < 4; i++)
          pv[i] = make_uint4(add_bf2(pv[i].x, pack_bf16(ct[8 * i], ct[8 * i + 1])), add_bf2(pv[i].y, pack_bf16(ct[8 * i + 2], ct[8 * i + 3])),
                             add_bf2(pv[i].z, pack_bf16(ct[8 * i + 4], ct[8 * i + 5])), add_bf2(pv[i].w, pack_bf16(ct[8 * i + 6], ct[8 * i + 7])));
        if (t == 5) to_owner(rb * 8 + 2 * ((q4 + 3) & 3) + 1 - rank, 3, 4);
#pragma unroll
        for (int i = 0; i < 4; i++) {
          if (t != 5)
            asm volatile("st.async.weak.shared::cluster.mbarrier::complete_tx::bytes.v4.b32 [%0], {%2,%3,%4,%5}, [%1];" ::"r"(peerZ - (t >> 1) * U + i * 512),
                         "r"(peerB + 16 * (t >> 1)), "r"(pv[i].x), "r"(pv[i].y), "r"(pv[i].z), "r"(pv[i].w) : "memory");
          wg_fence();
          tile_mma(IC<32>(), t, OA + i, OA + i + 1);
        }
        wg_commit();
      };
      asm volatile("barrier.cluster.wait.aligned;" ::: "memory");
      twait(bars + 8 * B_FT, 0, 0);
      wg_fence();
      tile_mma(IC<0>(), 0, 0, T0A);
      wg_commit();
      waitA(29 + wg);
      wg_wait<1>();
      mbar_arrive_if(elect, bars + 8 * (B_ET + 3));
      glu(cC, 32, 32, 0, 16);
      if (tid == 0) PROF_EV(6);
      if (tid == 128) PROF_EV(27);
      mbar_wait(bars + 8 * (j == 0 ? B_T : B_TL), 0);
      if (tid == 0) { PROF_EV(7); PROF_CK(45); }
      wg_fence();
      {
        const uint64_t dt = d128(dN + (OFF_T >> 4) + wg * 512), de = d128(dK + RING + (1 + wg) * 1024);
        mma_ss64<0, 1, 0>(ci, de, dt);
        mma_ss64<32, 1, 0>(ci, de + 512, dt);
#pragma unroll
        for (int k = 1; k < 4; k++) {
          mma_ss64<0, 1, 1>(ci, de + k * 2, dt + k * 128);
          mma_ss64<32, 1, 1>(ci, de + (512 + k * 2), dt + k * 128);
        }
        wg_commit();
      }
      tile_mma(IC<0>(), 0, T0A, T0B);
      wg_commit();
      wg_wait<1>();
      if (elect) asm volatile("mbarrier.arrive.shared::cluster.b64 _, [%0];" ::"r"(mapa(bars + 8 * B_RDY, rank ^ 1)) : "memory");
      mbar_arrive_if(elect, bars + 8 * (B_PZ + 1));
      fence_regs<0, 64>(ci);
#pragma unroll
      for (int i = 0; i < 16; i++) {
        const float gg = ((i & 1) ? g1 : g0) * (2.0f / (2048.0f * 512.0f));
        if (i & 2) yf[i] = pack_pin((ci[2 * i] - ci[28 + 2 * i]) * gg, (ci[2 * i + 1] - ci[29 + 2 * i]) * gg);
        else yf[i] = pack_pin((ci[2 * i] + ci[36 + 2 * i]) * gg, (ci[2 * i + 1] + ci[37 + 2 * i]) * gg);
      }
      even_end(0, T0B, true);
      if (tid == 0) PROF_EV(8);
      if (tid == 128) PROF_EV(28);
#pragma unroll 1
      for (int t = 1; t < 7; t += 2) {
        odd_head(t);
        wg_fence();
        tile_mma(IC<32>(), t, OA + 4, 14);
        wg_commit();
        const int zo = t >> 1, owner = rb * 8 + 2 * ((q4 + zo + 1) & 3) + rank;
        twait(bars + 8 * (B_FT + ((t + 1) & 3)), (t + 1) >> 2, t + 1);
        wg_fence();
        tile_mma(IC<0>(), t + 1, 0, TH);
        wg_commit();
        wg_wait<1>();
        mbar_arrive_if(elect && t < 5, bars + 8 * (B_ET + t));
        fence_regs<32, 32>(ct);
        if (t == 5) {
#pragma unroll
          for (int i = 0; i < 4; i++)
            pv[i] = make_uint4(pack_bf16(ct[32 + 8 * i], ct[33 + 8 * i]), pack_bf16(ct[34 + 8 * i], ct[35 + 8 * i]), pack_bf16(ct[36 + 8 * i], ct[37 + 8 * i]),
                               pack_bf16(ct[38 + 8 * i], ct[39 + 8 * i]));
          to_owner(owner, 2, 2 + wg);
        } else {
          fetch(pv, zo);
        }
        wg_fence();
        tile_mma(IC<0>(), t + 1, TH, EB);
        wg_commit();
        if (t != 5) {
#pragma unroll
          for (int i = 0; i < 4; i++)
            pv[i] = make_uint4(add_bf2(pv[i].x, pack_bf16(ct[32 + 8 * i], ct[33 + 8 * i])), add_bf2(pv[i].y, pack_bf16(ct[34 + 8 * i], ct[35 + 8 * i])),
                               add_bf2(pv[i].z, pack_bf16(ct[36 + 8 * i], ct[37 + 8 * i])), add_bf2(pv[i].w, pack_bf16(ct[38 + 8 * i], ct[39 + 8 * i])));
          to_owner(owner, zo, zo);
        }
        even_end(t + 1, EB, false);
      }
      {
        uint4 p1[4], p2[4];
        auto acc4 = [&](uint4 (&d)[4], const uint4 (&a)[4]) {
#pragma unroll
          for (int i = 0; i < 4; i++) { d[i].x = add_bf2(d[i].x, a[i].x); d[i].y = add_bf2(d[i].y, a[i].y); d[i].z = add_bf2(d[i].z, a[i].z); d[i].w = add_bf2(d[i].w, a[i].w); }
        };
        auto add32 = [&](const uint4 (&a)[4]) {
#pragma unroll
          for (int i = 0; i < 4; i++) {
            const uint32_t u[4] = {a[i].x, a[i].y, a[i].z, a[i].w};
#pragma unroll
            for (int e = 0; e < 4; e++) { ct[32 + 8 * i + 2 * e] += bf_lo(u[e]); ct[33 + 8 * i + 2 * e] += bf_hi(u[e]); }
          }
        };
        odd_head(7);
        fetch(pv, 4);
        fetch(p1, 5);
        wg_fence();
        tile_mma(IC<32>(), 7, OA + 4, OB);
        wg_commit();
        uint32_t bad = 0;
#pragma unroll
        for (int i = 0; i < 4; i++) { bad |= (pv[i].x ^ tag) | (p1[i].x ^ tag); pv[i].x &= ~1u; p1[i].x &= ~1u; }
        acc4(pv, p1);
        fetch(p2, 2);
        fetch(p1, 3);
        wg_fence();
        tile_mma(IC<32>(), 7, OB, 14);
        wg_commit();
        if (tid == 0) { PROF_EV(9); PROF_CK(46); }
        if (tid == 128) PROF_EV(29);
        uint4 p3[4];
#pragma unroll
        for (int i = 0; i < 4; i++) { bad |= p2[i].x ^ tag; p2[i].x &= ~1u; }
        acc4(p2, p1);
        fetch(p3, 6);
        if (tid == 0) PROF_EV(24);
        wg_wait<0>();
        fence_regs<32, 32>(ct);
#pragma unroll
        for (int i = 0; i < 4; i++) bad |= p3[i].x ^ tag;
        if (__any_sync(0xffffffffu, bad & 1)) {
          const uint4* src = ws->part + (size_t)(rb * 8 + j) * 4096 + fo;
          uint4 p0[4];
          int n = 0;
          do {
            bad = 0;
#pragma unroll
            for (int i = 0; i < 4; i++) {
              pv[i] = ld_x4(src + i * 32); p0[i] = ld_x4(src + 1024 + i * 32); p3[i] = ld_x4(src + 2048 + i * 32); p2[i] = ld_x4(src + 3072 + i * 32);
              bad |= (pv[i].x ^ tag) | (p0[i].x ^ tag) | (p2[i].x ^ tag) | (p3[i].x ^ tag);
            }
            if (++n > (1 << 21)) __trap();
          } while (__any_sync(0xffffffffu, bad & 1));
#pragma unroll
          for (int i = 0; i < 4; i++) { pv[i].x &= ~1u; p0[i].x &= ~1u; p2[i].x &= ~1u; }
          acc4(pv, p0); acc4(p2, p1);
        }
#pragma unroll
        for (int i = 0; i < 4; i++) p3[i].x &= ~1u;
        acc4(p2, p3);
        add32(pv); add32(p2);
#pragma unroll
        for (int i = 0; i < 4; i++)
          pv[i] = make_uint4(pack_bf16(ct[32 + 8 * i], ct[33 + 8 * i]), pack_bf16(ct[34 + 8 * i], ct[35 + 8 * i]), pack_bf16(ct[36 + 8 * i], ct[37 + 8 * i]), pack_bf16(ct[38 + 8 * i], ct[39 + 8 * i]));
        if (tid == 0) PROF_EV(14);
        const uint32_t stg = sb + OFF_T + warp * 2048;
        const int mr = (lane & 7) + ((lane >> 3) & 1) * 8, mc = lane >> 4;
#pragma unroll
        for (int i = 0; i < 4; i++)
          asm volatile("stmatrix.sync.aligned.m8n8.x4.shared.b16 [%0], {%1,%2,%3,%4};" ::"r"(stg + mr * 128 + (((2 * i + mc) ^ (mr & 7)) << 4)), "r"(pv[i].x),
                       "r"(pv[i].y), "r"(pv[i].z), "r"(pv[i].w) : "memory");
        __syncwarp();
#pragma unroll
        for (int i = 0; i < 4; i++) {
          const int r = 4 * i + (lane >> 3), c = lane & 7;
          const uint4 v = *(const uint4*)(smem + OFF_T + warp * 2048 + r * 128 + ((c ^ (r & 7)) << 4));
          *(uint4*)(out + (size_t)(2 * rb + wg + 32 * (16 * w + r)) * 512 + 64 * (q4 + 4 * rank) + 8 * c) = v;
        }
      }
      if (tid == 0) { PROF_EV(15); PROF_CK(41); }
      if (tid == 128) PROF_EV(30);
    }
  } else if (warp < 12) {
    asm volatile("setmaxnreg.dec.sync.aligned.u32 104;");
    asm volatile("barrier.cluster.arrive.relaxed.aligned;" ::: "memory");
    const int t = tid - 256, w = warp - 8;
    const uint32_t ep = ld_x1(&ws->epoch[blockIdx.x * 8]);
    const uint32_t tag = (ep + 1) & 1;
    auto w_issue = [&](const CUtensorMap* m) {

      if (elect_one()) { mbar_expect_tx(bars + 8 * (B_WR + w), 3072); tma4d(sb + OFF_T + w * 3072, m, bars + 8 * (B_WR + w), 32 * j, 0, 4 * (rb & 1) + w, rb >> 1); }

          __syncwarp();
    };
    auto gate_rows = [&] {
      const int r = 16 * j + 4 * w + (lane >> 3);
      const uint4* pg = (const uint4*)gate_w + (lane & 7);
      {
        float a = 0.f;
        asm volatile("bar.sync 4, 256;" ::: "memory");
#pragma unroll 1
        for (int hf = 0; hf < 2; hf++) {
          uint4 v[4], u[4];
#pragma unroll
          for (int kb = 0; kb < 4; kb++) v[kb] = __ldg(pg + (4 * hf + kb) * 8);
          mbar_wait(bars + 8 * (B_FE + 1 + 2 * hf), 0);
          if (hf) w_issue(&maps.wr);
#pragma unroll
          for (int kb = 0; kb < 4; kb++) u[kb] = *(const uint4*)(smem + (4 * hf + kb) * U + r * 128 + (((lane ^ r) & 7) << 4));
#pragma unroll
          for (int kb = 0; kb < 4; kb++) {
            const uint32_t uu[4] = {u[kb].x, u[kb].y, u[kb].z, u[kb].w}, vv[4] = {v[kb].x, v[kb].y, v[kb].z, v[kb].w};
#pragma unroll
            for (int e = 0; e < 4; e++) {
              uint32_t pr;
              asm("mul.rn.bf16x2 %0, %1, %2;" : "=r"(pr) : "r"(uu[e]), "r"(vv[e]));
              a += bf_lo(pr) + bf_hi(pr);
            }
          }
        }
#pragma unroll
        for (int o = 4; o; o >>= 1) a += __shfl_xor_sync(0xffffffffu, a, o);
        if ((lane & 7) == 0)
          asm volatile("st.relaxed.gpu.global.u32 [%0], %1;" ::"l"(ws->gate + rb * 128 + r),
                       "r"(pack_bf16(0.f, __fdividef(1.0f, 1.0f + __expf(-bf_lo(pack_bf16(a, 0.f))))) | tag) : "memory");
        if (t == 0) PROF_EV(18);
      }
    };
    {
      const int g = lane >> 2, q = lane & 3;
      uint32_t wf[32];
      if (!helper) {
        gate_rows();
        const uint32_t wa = sb + OFF_T + w * (3072 + 2) + (rb & 1) * 8 + q * 96 + g * 4, wb[2] = {wa + (rb & 1) * 32, wa + 32 - (rb & 1) * 32};
#pragma unroll 1
        for (int ri = 0; ri < 2; ri++) {
          mbar_wait(bars + 8 * (B_WR + w), ri);
#pragma unroll
          for (int n2 = 0; n2 < 32 / WB; n2++) {
            uint32_t v[WB];
#pragma unroll
            for (int i = 0; i < WB; i++) {
              const int e = n2 * WB + i;
              asm volatile("ld.shared.u16 %0, [%1];" : "=r"(v[i]) : "r"(wb[e & 1] + ((e >> 1) & 7) * 384 + (e >> 4) * 2) : "memory");
            }
#pragma unroll
            for (int i = 0; i < WB; i++) wf[n2 * WB + i] = __byte_perm(wf[n2 * WB + i], v[i], 0x5432);
            if (WSLEEP) { asm volatile("nanosleep.u32 %0;" ::"r"(WSLEEP + (v[WB - 1] >> 16)) : "memory"); }
          }
          __syncwarp();
          if (ri == 0) w_issue(&maps.wi);
        }
        asm volatile("bar.sync 1, 128;" ::: "memory");
        if (t == 0) PROF_EV(11);
      } else {
        asm volatile("bar.sync 4, 256;" ::: "memory");
        hint_wait(&ws->cntW[0], (ep + 1) * 128u);
        const uint32_t t0 = (uint32_t)clock();
#pragma unroll 1
        for (;;) {
          uint32_t bad = 0;
#pragma unroll
          for (int i = 0; i < 32; i++) {
            const float2 v = ld_x2((const float2*)ws->Wh + (i >> 4) * 2048 + 16 * w + g + 8 * (i & 1) + 64 * q + ((i >> 1) & 7) * 256);
            wf[i] = __float_as_uint(v.x); bad |= __float_as_uint(v.y) ^ tag;
          }
          if (!__any_sync(0xffffffffu, bad & 1)) break;
          spin_guard(t0);
        }
        if (t == 0) PROF_EV(11);
      }
      if (w == 0 && elect_one()) { mbar_expect_tx(bars + 8 * B_W, 8192); bulk_load(sb + OFF_D, dtab, 8192, bars + 8 * B_W); }
      asm volatile("barrier.cluster.wait.aligned;" ::: "memory");
      mbar_wait(bars + 8 * B_W, 0);
      mbar_wait(bars + 8 * B_HX, 0);
      if (t == 0) PROF_EV(12);
      const uint32_t dd = (sb & 0x3FFFF) >> 4;
      const uint64_t dF = d128((dd + (OFF_D >> 4)) | (512u << 16)), dI = d128((dd + (OFF_D >> 4)) | (1u << 16)), dA = d128((dd + (OFF_XB >> 4)) | (512u << 16));
      float az[32];
      const int zero = blockIdx.x >> 16;
      uint32_t pf[32];
#pragma unroll
      for (int mt = 0; mt < 2; mt++) {
        wg_fence();
        if (mt == 0) mma_ss64<0, 3, 0>(az, dA, dF);
        else mma_ss64<0, 3, 2>(az, dA + 512, dF, zero);
#pragma unroll
        for (int k = 1; k < 4; k++) mma_ss64<0, 3, 1>(az, dA + (mt * 512 + k * 128), dF + k * 128);
        wg_commit();
        wg_wait<0>();
        fence_regs<0, 32>(az);
#pragma unroll
        for (int i = 0; i < 16; i++) {
          const float wr = bf_lo(wf[16 * mt + i]), wi = bf_hi(wf[16 * mt + i]);
          pf[16 * mt + i] = pack_pin(fmaf(az[2 * i], wr, -az[2 * i + 1] * wi), fmaf(az[2 * i], wi, az[2 * i + 1] * wr));
        }
      }
      if (t == 0) PROF_EV(16);
      {
        const int m = lane >> 3, r = lane & 7;
        const int sl = 2 * (m >> 1) + ((r >> 1) & 1) + 4 * (r >> 2);
        const uint32_t a0 = sb + OFF_XB + w * 4096 + sl * 64 + (((((m ^ rb) & 1) * 2 + (r & 1)) ^ (sl >> 1)) << 4);
        uint32_t pk[16];
#pragma unroll
        for (int mt = 0; mt < 3; mt++) {
          if (mt < 2) {
            wg_fence();
            mma_rs64<0, 0, 2>(az, pf[16 * mt], pf[16 * mt + 1], pf[16 * mt + 2], pf[16 * mt + 3], dI, mt ? (int)helper : zero);
#pragma unroll
            for (int k = 1; k < 4; k++) mma_rs64<0, 0, 1>(az, pf[16 * mt + 4 * k], pf[16 * mt + 4 * k + 1], pf[16 * mt + 4 * k + 2], pf[16 * mt + 4 * k + 3], dI + k * 2);
            wg_commit();
          }
          if (mt > 0 && !helper) {
#pragma unroll
            for (int i = 0; i < 4; i++) stsm4t(a0 + (mt - 1) * 2048 + i * 512, pk[4 * i], pk[4 * i + 1], pk[4 * i + 2], pk[4 * i + 3]);
          }
          if (mt < 2) {
            wg_wait<0>();
            fence_regs<0, 32>(az);
#pragma unroll
            for (int i = 0; i < 16; i++) pk[i] = pack_pin(az[2 * i], az[2 * i + 1]);
          }
        }
      }
      if (helper) {
#pragma unroll
        for (int i = 0; i < 16; i++) {
          const int n = i >> 1, s0 = 8 * (n >> 1) + 2 * (n & 1) + (q & 1) + 4 * (q >> 1);
          if ((n & 1) == (int)(blockIdx.x & 1)) st_u2(ws->Ts + s0 * 64 + 16 * w + g + 8 * (i & 1), pack_bf16(az[2 * i], az[2 * i + 1]), tag);
        }
        __syncwarp();
        hint_add_if(lane == 0, &ws->cntH[0]);
        if (t == 0) { ws->epoch[blockIdx.x * 8] = ep + 1; PROF_EV(13); }
      } else {
        asm volatile("fence.proxy.async.shared::cta;" ::: "memory");
        __syncwarp();
        if (elect_one()) {
          if (t == 0) PROF_EV(17);
          if (SPACE) __nanosleep(SPACE * w);
          asm volatile("cp.async.bulk.tensor.4d.global.shared::cta.bulk_group [%0, {%2, %3, %4, %5}], [%1];" ::"l"(&maps.ts), "r"(sb + OFF_XB + w * 4096),
                       "r"(32 * rank), "r"(0), "r"(2 * q4), "r"(4 * rb + w) : "memory");
          bulk_done_signal(&ws->cntT[32 * q4]);
          asm volatile("mbarrier.arrive.shared::cluster.b64 _, [%0];" ::"r"(mapa(bars + 8 * B_RD0, rank ^ 1)) : "memory");
          if (t == 96) PROF_EV(13);
        }
        __syncwarp();
        if (j == 0) {
          hint_wait(&ws->cntH[0], (ep + 1) * 8u);
          const uint32_t t0 = (uint32_t)clock();
          float2 v;
          do { v = ld_x2((const float2*)ws->Ts + 2 * rb * 64 + t); spin_guard(t0); } while (__any_sync(0xffffffffu, (__float_as_uint(v.y) ^ tag) & 1));
          mbar_wait(bars + 8 * B_TL, 0);
          const uint32_t u = __float_as_uint(v.x);
          *(uint16_t*)(smem + OFF_T + t * 128 + ((t & 7) << 4)) = (uint16_t)u;
          *(uint16_t*)(smem + OFF_T + t * 128 + (((t & 7) ^ 1) << 4)) = (uint16_t)(u >> 16);
          asm volatile("fence.proxy.async.shared::cta;" ::: "memory");
          __syncwarp();
          mbar_arrive_if(lane == 0, bars + 8 * B_T);
        }
      }
    }
  } else {
    asm volatile("setmaxnreg.dec.sync.aligned.u32 24;");
    auto xf_load = [&](int q) {
      const uint32_t fb = bars + 8 * (B_FX + q);
      mbar_expect_tx(fb, U + 8192);
      tma3d(sb + q * U, &maps.x, fb, 64 * q, 0, 2 * rb);
      if (q >= 4) mbar_wait(bars + 8 * (B_FE + ((q - 4) >> 1)), 0);
      tma2d(sb + OFF_XB + (q & 3) * 8192, &maps.ft, fb, 64 * q, 64 * j);
    };
    if (elect_one()) {
      if (warp == 14) {
#pragma unroll
        for (int i = 0; i < B_FT; i++) mbar_init(bars + 8 * i, 1);
        asm volatile("fence.mbarrier_init.release.cluster;" ::: "memory");
        if (!helper) {
#pragma unroll 1
          for (int n = 0; n < 2; n++) {
            const uint32_t fb = bars + 8 * (B_FA + n);
            xf_load(2 * n); xf_load(2 * n + 1);
            mbar_expect_tx(fb, U);
            tma2d(sb + OFF_RING + n * U, &maps.g64, fb, f_full, 64 * n);
            tma2d(sb + OFF_RING + n * U + 8192, &maps.u64, fb, f_full, 64 * n);
          }
        }
      } else if (warp == 15) {
#pragma unroll
        for (int i = B_FT; i < NBAR; i++) mbar_init(bars + 8 * i, i < B_EA ? 1 : i < B_T ? 2 : 4);
#pragma unroll
        for (int i = 0; i < 8; i++) if (i != 4) mbar_expect_tx(bars + 8 * (B_Z + i), U / 2);
        asm volatile("fence.mbarrier_init.release.cluster;" ::: "memory");
        asm volatile("fence.proxy.async.shared::cta;" ::: "memory");
      }
    }
    __syncwarp();
    asm volatile("bar.arrive 0, 384;" ::: "memory");
    asm volatile("bar.arrive 4, 256;" ::: "memory");
    __syncwarp();
    asm volatile("barrier.cluster.arrive.relaxed.aligned;" ::: "memory");
    asm volatile("bar.sync 3, 128;" ::: "memory");
    if (warp == 15 && !helper) {
        mbar_wait(bars + 8 * B_FE, 0);
        const uint32_t tag = (ld_x1(&ws->epoch[blockIdx.x * 8]) + 1) & 1;
        const int c = lane >> 4, jj = 16 * blockIdx.x + (lane & 15), jm = (2048 - jj) & 2047;
        const unsigned short* pr = (const unsigned short*)w_r + 256 * c;
        const unsigned short* pi = (const unsigned short*)w_i + 256 * c;
        const float wr = 0.25f * (bf_lo(__ldg(pr + jj * 257)) + bf_lo(__ldg(pr + jm * 257)));
        const float wi = 0.25f * (bf_lo(__ldg(pi + jj * 257)) - bf_lo(__ldg(pi + jm * 257)));
        st_u2(ws->Wh + c * 2048 + jj, c ? pack_bf16(-wi, wr) : pack_bf16(wr, wi), tag);
        __syncwarp();
        hint_add_if(lane == 0, &ws->cntW[0]);
        mbar_wait(bars + 8 * B_XS, 0);
        const uint32_t t0 = (uint32_t)clock();
        uint4 v;
        do { v = ld_x4(ws->gate + rb * 128 + 4 * lane); spin_guard(t0); } while (__any_sync(0xffffffffu, ((v.x ^ tag) | (v.y ^ tag) | (v.z ^ tag) | (v.w ^ tag)) & 1));
        *(uint4*)(smem + OFF_G + lane * 16) = v;
        __syncwarp();
        mbar_arrive_if(lane < 4, bars + 8 * B_G);
      }
    auto part_load = [&](int i, unsigned ep1) {
      const bool half = (i >> 1) == 1;
      const uint32_t bytes = half ? U / 2 : U, bar = bars + 8 * (i == 4 ? B_Z + 4 : B_HP + i);
      mbar_wait(bars + 8 * (B_PZ + (i == 0)), 0);
      mbar_expect_tx(bar, bytes);
      flag_wait(&ws->cntP[64 * (rb * 8 + j) + 8 * i], ep1 * (half ? 4u : 8u));
      bulk_load(sb + (i == 0 ? OFF_T : i == 1 ? 0 : half ? i * (U / 2) : OFF_Z - 2 * U), ws->part + (size_t)(rb * 8 + j) * 4096 + (i < 2 ? i * 1024 : 1024 + i * 512), bytes, bar);
      if (i == 2) PROF_EV(26);
    };
    if ((!helper || warp == 15) && elect_one()) {
      if (warp < 14) {
        const int p = warp - 12;
#pragma unroll 1
        for (int i = 4 + p; i < 14; i += 2) asm volatile("prefetch.tensormap [%0];" ::"l"((const char*)&maps + i * 128) : "memory");
#pragma unroll 1
        for (int n = 2; n < 31; n++) {
          const bool table = n == 4 || n >= 29;
          const bool half = n >= 17 && n < 21;
          const int q = n < 4 ? n : n < 17 ? n - 1 : n - 5;
          const CUtensorMap* m = table ? &maps.e : half ? &maps.g32 + p : &maps.g64 + p;
          const int c0 = table ? 0 : half ? f_half : f_full + 64 * (q >> 3);
          const int c1 = table ? (2 * rb + ((n & 1) ^ 1)) * 128 + 64 * p : half ? 128 * (n - 17) : 64 * (q & 7);
          const uint32_t fb = bars + 8 * (B_FA + (n & 3)), dst = sb + OFF_RING + (n & 3) * U + p * 8192;
          if (n < 4) mbar_wait(bars + 8 * (B_FE + n - 2), 0);
          else mbar_wait(bars + 8 * (B_EA + (n & 3)), ((n >> 2) & 1) ^ 1);
          tma2d(dst, m, fb, c0, c1);
          if (p == 0) mbar_expect_tx(fb, U);
        }
        part_load(2 + p, ld_x1(&ws->epoch[blockIdx.x * 8]) + 1);
      } else if (warp == 15) {
        const unsigned ep1 = ld_x1(&ws->epoch[blockIdx.x * 8]) + 1;
        flag_wait(&ws->cntX[helper ? 0 : 32 * j], ep1 * 16u);
        PROF_EV(22);
        mbar_expect_tx(bars + 8 * B_HX, U);
        bulk_load(sb + OFF_XB, ws->X + (size_t)(helper ? 128 : 16 * j + rb) * 8192, U, bars + 8 * B_HX);
        if (!helper) {
          flag_wait(&ws->cntT[32 * q4], ep1 * 128u);
          PROF_EV(23);
          mbar_expect_tx(bars + 8 * B_TL, U);
          tma3d(sb + OFF_T, &maps.t, bars + 8 * B_TL, 64 * j, 0, 2 * rb);
          part_load(0, ep1); part_load(1, ep1); part_load(4, ep1);
          mbar_wait(bars + 8 * (B_HP + 2), 0); mbar_wait(bars + 8 * (B_HP + 3), 0);
          ws->epoch[blockIdx.x * 8] = ep1;
        }
      } else {
#pragma unroll 1
        for (int q = 4; q < 8; q++) xf_load(q);
        mbar_wait(bars + 8 * (B_FE + 2), 0);
        mbar_expect_tx(bars + 8 * B_E0, U);
        tma2d(sb + OFF_XB, &maps.e, bars + 8 * B_E0, 0, 2 * rb * 128);
        tma2d(sb + OFF_XB + 8192, &maps.e, bars + 8 * B_E0, 0, 2 * rb * 128 + 64);
#pragma unroll 1
        for (int h2 = 0; h2 < 2; h2++) {
          const int s0 = 2 * rb + h2, sg = (s0 & ~6) | ((s0 & 2) << 1) | ((s0 & 4) >> 1);
          mbar_wait(bars + 8 * (B_XS + h2), 0);
#pragma unroll 1
          for (int c = 0; c < 2; c++) {
            asm volatile("cp.async.bulk.tensor.4d.global.shared::cta.bulk_group [%0, {%2, %3, %4, %5}], [%1];" ::"l"(&maps.xs),
                         "r"(sb + OFF_XB + h2 * 8192 + c * 4096), "r"(0), "r"(sg), "r"(0), "r"(16 * j + 8 * c) : "memory");
            if (j == 0)
              asm volatile("cp.async.bulk.global.shared::cta.bulk_group [%0], [%1], 256;" ::"l"(ws->X + 128 * 8192 + c * 4096 + sg * 128),
                           "r"(sb + OFF_SP + h2 * 512 + c * 256) : "memory");
            if (SPACE && h2 + c < 2) __nanosleep(SPACE);
          }
        }
        bulk_done_signal(&ws->cntX[32 * j]);
        PROF_EV(20);
#pragma unroll 1
        for (int t = 0; t < 8; t++) {
          const int col = 64 * (((q4 + 1 + (t >> 1)) & 3) + 4 * ((t & 1) ? rank : 1 - rank));
          const uint32_t fb = bars + 8 * (B_FT + (t & 3)), dst = sb + (t & 3) * TB;
          mbar_wait(bars + 8 * (B_ET + (t < 3 ? t + 1 : t & 3)), t >> 2);
          mbar_expect_tx(fb, (t & 1) ? 28672 : TB);
          tma2d(dst, &maps.d224, fb, col, 224 * j);
          if (!(t & 1)) tma3d(dst + 28672, &maps.fg, fb, col ^ 256, 16 * rank, 4 * q4);
        }
      }
    }
  }
}

typedef CUresult (*EncodeFn)(CUtensorMap*, CUtensorMapDataType, cuuint32_t, void*, const cuuint64_t*, const cuuint64_t*, const cuuint32_t*,
                             const cuuint32_t*, CUtensorMapInterleave, CUtensorMapSwizzle, CUtensorMapL2promotion, CUtensorMapFloatOOBfill);

static void encode(EncodeFn f, CUtensorMap* m, const void* base, int rank, const cuuint64_t* dims, const cuuint64_t* strides, const cuuint32_t* box,
                   CUtensorMapSwizzle sw) {
  cuuint32_t es[5] = {1, 1, 1, 1, 1};
  f(m, CU_TENSOR_MAP_DATA_TYPE_BFLOAT16, rank, (void*)base, dims, strides, box, es, CU_TENSOR_MAP_INTERLEAVE_NONE, sw,
    CU_TENSOR_MAP_L2_PROMOTION_L2_128B, CU_TENSOR_MAP_FLOAT_OOB_FILL_NONE);
}

extern "C" void kernel_launch(void* const* d_in, const int* in_sizes, int n_in, void* d_out, int out_size) {
  (void)in_sizes; (void)n_in; (void)out_size;
  const __nv_bfloat16* x = (const __nv_bfloat16*)d_in[0];
  const __nv_bfloat16* w_r = (const __nv_bfloat16*)d_in[1];
  const __nv_bfloat16* w_i = (const __nv_bfloat16*)d_in[2];
  const __nv_bfloat16* Wg = (const __nv_bfloat16*)d_in[4];
  const __nv_bfloat16* Wu = (const __nv_bfloat16*)d_in[5];
  const __nv_bfloat16* Wd = (const __nv_bfloat16*)d_in[6];
  const __nv_bfloat16* gw = (const __nv_bfloat16*)d_in[7];

  void* fp = nullptr; cudaDriverEntryPointQueryResult qr;
  cudaGetDriverEntryPoint("cuTensorMapEncodeTiled", &fp, cudaEnableDefault, &qr);
  EncodeFn enc = (EncodeFn)fp;
  void *pFT, *pET, *pDT, *pW;
  cudaGetSymbolAddress(&pDT, g_DT); cudaGetSymbolAddress(&pW, g_work);
  void *pX = ((Work*)pW)->X, *pT = ((Work*)pW)->T;
  cudaGetSymbolAddress(&pFT, g_FT); cudaGetSymbolAddress(&pET, g_ET);

  Maps mp;
  const CUtensorMapSwizzle S128 = CU_TENSOR_MAP_SWIZZLE_128B, S64 = CU_TENSOR_MAP_SWIZZLE_64B;
  { cuuint64_t d[3] = {512, 64, 32}, s[2] = {32768, 1024}; cuuint32_t b[3] = {64, 64, 2}; encode(enc, &mp.x, x, 3, d, s, b, S128); }
  { cuuint64_t d[2] = {512, 512}, s[1] = {1024}; cuuint32_t b[2] = {64, 64}; encode(enc, &mp.ft, pFT, 2, d, s, b, S128); }
  { cuuint64_t d[4] = {128, 32, 2, 129}, s[3] = {256, 8192, 16384}; cuuint32_t b[4] = {128, 1, 2, 8}; encode(enc, &mp.xs, pX, 4, d, s, b, CU_TENSOR_MAP_SWIZZLE_NONE); }
  { cuuint64_t d[4] = {64, 32, 8, 64}, s[3] = {65536, 128, 1024}; cuuint32_t b[4] = {32, 32, 2, 1}; encode(enc, &mp.ts, pT, 4, d, s, b, S64); }
  { cuuint64_t d[3] = {512, 32, 16}, s[2] = {1024, 32768}; cuuint32_t b[3] = {64, 16, 4}; encode(enc, &mp.fg, pFT, 3, d, s, b, S128); }
  { cuuint64_t d[3] = {512, 64, 32}, s[2] = {1024, 65536}; cuuint32_t b[3] = {64, 64, 2}; encode(enc, &mp.t, pT, 3, d, s, b, S128); }
  { cuuint64_t d[2] = {64, 4096}, s[1] = {128}; cuuint32_t b[2] = {64, 64}; encode(enc, &mp.e, pET, 2, d, s, b, S128); }
  { cuuint64_t d[2] = {1792, 512}, s[1] = {3584}; cuuint32_t b[2] = {64, 64}, b2[2] = {32, 128};
    encode(enc, &mp.g64, Wg, 2, d, s, b, S128); encode(enc, &mp.u64, Wu, 2, d, s, b, S128);
    encode(enc, &mp.g32, Wg, 2, d, s, b2, S64); encode(enc, &mp.u32, Wu, 2, d, s, b2, S64); }
  { cuuint64_t d[2] = {512, 1792}, s[1] = {1024}; cuuint32_t b[2] = {64, 224}; encode(enc, &mp.d224, Wd, 2, d, s, b, S128); }
  { cuuint64_t d[4] = {264, 32, 8, 8}, s[3] = {32896, 512, 4112}; cuuint32_t b[4] = {48, 32, 1, 1};
    encode(enc, &mp.wr, w_r, 4, d, s, b, CU_TENSOR_MAP_SWIZZLE_NONE); encode(enc, &mp.wi, w_i, 4, d, s, b, CU_TENSOR_MAP_SWIZZLE_NONE); }

  cudaFuncSetAttribute(fused_kernel, cudaFuncAttributeMaxDynamicSharedMemorySize, SMEM_BYTES);
  fused_kernel<<<NCTA, 512, SMEM_BYTES>>>((Work*)pW, (const uint16_t*)pDT, w_r, w_i, gw, x, (__nv_bfloat16*)d_out, mp);
}
```

```cpp
#include <cuda_runtime.h>
#include <cuda_bf16.h>
#include <cuda.h>
#include <stdint.h>

namespace tbl {
constexpr double PI = 3.14159265358979323846264338327950288;
constexpr double sin_s(double x) { double t = x, s = x; for (int n = 1; n < 12; n++) { t *= -x * x / ((2 * n) * (2 * n + 1)); s += t; } return s; }
constexpr double cos_s(double x) { double t = 1, s = 1; for (int n = 1; n < 12; n++) { t *= -x * x / ((2 * n - 1) * (2 * n)); s += t; } return s; }
constexpr double cos2048(int m) {
  m &= 2047; if (m > 1024) m = 2048 - m;
  bool neg = false; if (m > 512) { m = 1024 - m; neg = true; }
  double v = (m <= 256) ? cos_s(2 * PI * m / 2048) : sin_s(2 * PI * (512 - m) / 2048);
  return neg ? -v : v;
}
constexpr uint16_t to_bf16(double v) {
  if (v == 0) return 0;
  uint16_t s = 0; if (v < 0) { s = 0x8000; v = -v; }
  int e = 0; while (v >= 2) { v /= 2; e++; } while (v < 1) { v *= 2; e--; }
  double m = (v - 1) * 128; int mi = (int)m; double fr = m - mi;
  if (fr > 0.5 || (fr == 0.5 && (mi & 1))) mi++;
  if (mi == 128) { mi = 0; e++; }
  return (uint16_t)(s | ((e + 127) << 7) | mi);
}
struct CosT { uint16_t v[2048]; constexpr CosT() : v() { for (int i = 0; i < 2048; i++) v[i] = to_bf16(cos2048(i)); } };
struct alignas(1024) FT {
  uint16_t v[512 * 512];
  constexpr FT() : v() {
    CosT c;
    for (int r = 0; r < 512; r++) {
      int k = (r >> 5) * 16 + 2 * (r & 7) + ((r >> 4) & 1), e = (r >> 3) & 1;
      int mul = 4 * k, add = e ? 512 : 0;
      if (k == 0 && e == 1) { mul = 1024; add = 0; }
      for (int d = 0; d < 512; d++) v[r * 512 + d] = c.v[(d * mul + add) & 2047];
    }
  }
};
struct alignas(1024) ET {
  uint16_t v[2 * 32 * 4096];
  constexpr ET() : v() {
    CosT c;
    for (int s = 0; s < 1024; s++)
      for (int j1 = 0; j1 < 64; j1++)
        for (int e = 0; e < 2; e++) {
          const int s0 = s & 31, i = s >> 5, p = j1 & 1, j = j1 >> 1;
          const uint16_t x = c.v[(s * j1 + 512 * e) & 2047];
          v[s0 * 4096 + (p * 32 + i) * 64 + e * 32 + j] = x;
          v[(32 + s0) * 4096 + ((i >> 3) * 16 + e * 8 + (i & 7)) * 64 + p * 32 + j] = x;
        }
  }
};
struct alignas(1024) DT {
  uint16_t v[64 * 64];
  constexpr DT() : v() {
    CosT c;
    for (int r = 0; r < 64; r++)
      for (int n = 0; n < 64; n++) {
        const int sg = r >> 1, s0 = (sg & ~6) | ((sg & 2) << 1) | ((sg & 4) >> 1), e = r & 1, f = n & 1;
        const int m = 64 * s0 * (n >> 1) + (e == f ? 0 : e ? -512 : 512);
        v[r * 64 + (((n >> 3) ^ (r & 7)) << 3) + (n & 7)] = c.v[m & 2047];
      }
  }
};
}

__device__ constexpr tbl::FT g_FT = tbl::FT();
__device__ constexpr tbl::ET g_ET = tbl::ET();
__device__ constexpr tbl::DT g_DT = tbl::DT();

struct alignas(1024) Work {
  unsigned epoch[132 * 8];
  unsigned cntX[8 * 32], cntT[8 * 32], cntP[128 * 32], cntW[32], cntH[32];
  alignas(16) float gate[16 * 128];
  alignas(16) uint2 Wh[2 * 2048];
  alignas(16) uint2 Ts[32 * 64];
  alignas(1024) uint16_t X[129 * 8192];
  alignas(1024) uint16_t T[32 * 64 * 512];
  alignas(1024) uint4 part[128 * 3 * 1024];
};
__device__ Work g_work;
#define PROF_EV(i) do {} while (0)
#define PROF_CK(i) do {} while (0)

__device__ __forceinline__ uint32_t smem_u32(const void* p) { return (uint32_t)__cvta_generic_to_shared(p); }
__device__ __forceinline__ void mbar_init(uint32_t bar, uint32_t cnt) { asm volatile("mbarrier.init.shared::cta.b64 [%0], %1;" ::"r"(bar), "r"(cnt)); }
__device__ __forceinline__ void mbar_expect_tx(uint32_t bar, uint32_t bytes) { asm volatile("mbarrier.arrive.expect_tx.shared::cta.b64 _, [%0], %1;" ::"r"(bar), "r"(bytes) : "memory"); }
__device__ __forceinline__ void mbar_arrive(uint32_t bar) { asm volatile("mbarrier.arrive.shared::cta.b64 _, [%0];" ::"r"(bar) : "memory"); }
__device__ __forceinline__ bool elect_one() {
  uint32_t p;
  asm volatile("{\n.reg .pred p;\nelect.sync _|p, 0xffffffff;\nselp.u32 %0, 1, 0, p;\n}" : "=r"(p));
  return p;
}
__device__ __forceinline__ void mbar_arrive_if(bool p, uint32_t bar) {
  asm volatile("{\n.reg .pred p;\nsetp.ne.b32 p, %1, 0;\n@p mbarrier.arrive.shared::cta.b64 _, [%0];\n}" ::"r"(bar), "r"((int)p) : "memory");
}
__device__ __forceinline__ void hint_add_if(bool p, unsigned* a) {
  asm volatile("{\n.reg .pred p;\nsetp.ne.b32 p, %1, 0;\n@p red.relaxed.gpu.global.add.u32 [%0], 1;\n}" ::"l"(a), "r"((int)p) : "memory");
}
__device__ __forceinline__ bool mbar_try(uint32_t bar, uint32_t parity) {
  uint32_t ok;
  asm volatile("{\n.reg .pred p;\nmbarrier.test_wait.parity.shared::cta.b64 p, [%1], %2;\nselp.u32 %0, 1, 0, p;\n}" : "=r"(ok) : "r"(bar), "r"(parity) : "memory");
  return ok;
}
__device__ __forceinline__ void mbar_wait(uint32_t bar, uint32_t parity) {
  asm volatile(
      "{\n.reg .pred p;\n.reg .u32 n;\nmov.u32 n, 0;\n"
      "W_LOOP:\nmbarrier.try_wait.parity.shared::cta.b64 p, [%0], %1;\n@p bra W_DONE;\n"
      "add.u32 n, n, 1;\nsetp.lt.u32 p, n, 0x40000;\n@p bra W_LOOP;\ntrap;\nW_DONE:\n}" ::"r"(bar), "r"(parity) : "memory");
}
__device__ __forceinline__ void bulk_load(uint32_t dst, const void* src, uint32_t bytes, uint32_t bar) {
  asm volatile("cp.async.bulk.shared::cluster.global.mbarrier::complete_tx::bytes [%0], [%1], %2, [%3];" ::"r"(dst), "l"(src), "r"(bytes), "r"(bar) : "memory");
}
__device__ __forceinline__ void spin_guard(uint32_t t0) { if ((uint32_t)clock() - t0 > (1u << 30)) __trap(); }
__device__ __forceinline__ float2 ld_x2(const float2* p) { float2 v; asm volatile("ld.relaxed.gpu.global.v2.f32 {%0,%1}, [%2];" : "=f"(v.x), "=f"(v.y) : "l"(p) : "memory"); return v; }
__device__ __forceinline__ void st_u2(uint2* p, uint32_t a, uint32_t b) { asm volatile("st.relaxed.gpu.global.v2.u32 [%0], {%1,%2};" ::"l"(p), "r"(a), "r"(b) : "memory"); }
__device__ __forceinline__ uint32_t ld_x1(const void* p) { uint32_t v; asm volatile("ld.relaxed.gpu.global.u32 %0, [%1];" : "=r"(v) : "l"(p) : "memory"); return v; }
__device__ __forceinline__ uint4 ld_x4(const void* p) { uint4 v; asm volatile("ld.relaxed.gpu.global.v4.u32 {%0,%1,%2,%3}, [%4];" : "=r"(v.x), "=r"(v.y), "=r"(v.z), "=r"(v.w) : "l"(p) : "memory"); return v; }
__device__ __forceinline__ uint32_t mapa(uint32_t a, uint32_t cta) { uint32_t r; asm volatile("mapa.shared::cluster.u32 %0, %1, %2;" : "=r"(r) : "r"(a), "r"(cta)); return r; }
__device__ __forceinline__ void stsm4t(uint32_t a, uint32_t r0, uint32_t r1, uint32_t r2, uint32_t r3) {
  asm volatile("stmatrix.sync.aligned.m8n8.x4.trans.shared.b16 [%0], {%1,%2,%3,%4};" ::"r"(a), "r"(r0), "r"(r1), "r"(r2), "r"(r3) : "memory");
}
__device__ __forceinline__ void hint_add(unsigned* p) { asm volatile("red.relaxed.gpu.global.add.u32 [%0], 1;" ::"l"(p) : "memory"); }
__device__ __forceinline__ void hint_wait(const unsigned* p, unsigned target) {
  const uint32_t t0 = (uint32_t)clock();
  while ((int)(ld_x1(p) - target) < 0) spin_guard(t0);
}
__device__ __forceinline__ void bulk_done_signal(unsigned* p) {
  asm volatile("cp.async.bulk.commit_group;\ncp.async.bulk.wait_group 0;\nfence.proxy.async.global;" ::: "memory");
  hint_add(p);
}
__device__ __forceinline__ void flag_wait(const unsigned* p, unsigned target) {
  hint_wait(p, target);
  asm volatile("fence.proxy.async.global;" ::: "memory");
}
__device__ __forceinline__ void tma2d(uint32_t dst, const CUtensorMap* m, uint32_t bar, int c0, int c1) {
  asm volatile("cp.async.bulk.tensor.2d.shared::cluster.global.mbarrier::complete_tx::bytes [%0], [%1, {%3, %4}], [%2];" ::"r"(dst), "l"(m), "r"(bar), "r"(c0), "r"(c1) : "memory");
}
__device__ __forceinline__ void tma3d(uint32_t dst, const CUtensorMap* m, uint32_t bar, int c0, int c1, int c2) {
  asm volatile("cp.async.bulk.tensor.3d.shared::cluster.global.mbarrier::complete_tx::bytes [%0], [%1, {%3, %4, %5}], [%2];" ::"r"(dst), "l"(m), "r"(bar), "r"(c0), "r"(c1), "r"(c2) : "memory");
}
__device__ __forceinline__ void tma4d(uint32_t dst, const CUtensorMap* m, uint32_t bar, int c0, int c1, int c2, int c3) {
  asm volatile("cp.async.bulk.tensor.4d.shared::cluster.global.mbarrier::complete_tx::bytes [%0], [%1, {%3, %4, %5, %6}], [%2];" ::"r"(dst), "l"(m), "r"(bar), "r"(c0), "r"(c1), "r"(c2), "r"(c3) : "memory");
}
__device__ __forceinline__ void tma5d(uint32_t dst, const CUtensorMap* m, uint32_t bar, int c0, int c4) {
  asm volatile("cp.async.bulk.tensor.5d.shared::cluster.global.mbarrier::complete_tx::bytes [%0], [%1, {%3, %5, %5, %5, %4}], [%2];" ::"r"(dst), "l"(m), "r"(bar), "r"(c0), "r"(c4), "r"(0) : "memory");
}
__device__ __forceinline__ void wg_fence() { asm volatile("wgmma.fence.sync.aligned;" ::: "memory"); }
__device__ __forceinline__ void wg_commit() { asm volatile("wgmma.commit_group.sync.aligned;" ::: "memory"); }
template <int N> __device__ __forceinline__ void wg_wait() { asm volatile("wgmma.wait_group.sync.aligned %0;" ::"n"(N) : "memory"); }
template <int O, int N, int NN> __device__ __forceinline__ void fence_regs(float (&d)[NN]) {
#pragma unroll
  for (int i = 0; i < N; i++) asm volatile("" : "+f"(d[O + i])::"memory");
}
__device__ __forceinline__ uint32_t pack_bf16(float lo, float hi) {
  uint32_t r; asm("cvt.rn.bf16x2.f32 %0, %1, %2;" : "=r"(r) : "f"(hi), "f"(lo)); return r;
}
__device__ __forceinline__ uint32_t pack_pin(float lo, float hi) {
  uint32_t r; asm volatile("cvt.rn.bf16x2.f32 %0, %1, %2;" : "=r"(r) : "f"(hi), "f"(lo) : "memory"); return r;
}
__device__ __forceinline__ uint32_t add_bf2(uint32_t a, uint32_t b) { uint32_t r; asm("add.rn.bf16x2 %0, %1, %2;" : "=r"(r) : "r"(a), "r"(b)); return r; }
__device__ __forceinline__ float bf_lo(uint32_t u) { return __uint_as_float(u << 16); }
__device__ __forceinline__ float bf_hi(uint32_t u) { return __uint_as_float(u & 0xffff0000u); }

__device__ __forceinline__ uint64_t d128(uint32_t lo) { uint64_t d; asm("mov.b64 %0, {%1, 0x40000040};" : "=l"(d) : "r"(lo)); return d; }
__device__ __forceinline__ uint64_t d64(uint32_t lo) { uint64_t d; asm("mov.b64 %0, {%1, 0x80000020};" : "=l"(d) : "r"(lo)); return d; }
template<int O,int TB,int ACC,int NN> __device__ __forceinline__ void mma_ss64(float (&d)[NN], uint64_t da, uint64_t db, int sd = 0){
  if constexpr (ACC == 1) asm volatile("wgmma.mma_async.sync.aligned.m64n64k16.f32.bf16.bf16 {%0,%1,%2,%3,%4,%5,%6,%7,%8,%9,%10,%11,%12,%13,%14,%15,%16,%17,%18,%19,%20,%21,%22,%23,%24,%25,%26,%27,%28,%29,%30,%31}, %32, %33, 1, 1, 1, %35, %34;"
   : "+f"(d[O+0]), "+f"(d[O+1]), "+f"(d[O+2]), "+f"(d[O+3]), "+f"(d[O+4]), "+f"(d[O+5]), "+f"(d[O+6]), "+f"(d[O+7]), "+f"(d[O+8]), "+f"(d[O+9]), "+f"(d[O+10]), "+f"(d[O+11]), "+f"(d[O+12]), "+f"(d[O+13]), "+f"(d[O+14]), "+f"(d[O+15]), "+f"(d[O+16]), "+f"(d[O+17]), "+f"(d[O+18]), "+f"(d[O+19]), "+f"(d[O+20]), "+f"(d[O+21]), "+f"(d[O+22]), "+f"(d[O+23]), "+f"(d[O+24]), "+f"(d[O+25]), "+f"(d[O+26]), "+f"(d[O+27]), "+f"(d[O+28]), "+f"(d[O+29]), "+f"(d[O+30]), "+f"(d[O+31])
   : "l"(da), "l"(db), "n"(TB & 1), "n"(TB >> 1));
  else if constexpr (ACC == 0) asm volatile("wgmma.mma_async.sync.aligned.m64n64k16.f32.bf16.bf16 {%0,%1,%2,%3,%4,%5,%6,%7,%8,%9,%10,%11,%12,%13,%14,%15,%16,%17,%18,%19,%20,%21,%22,%23,%24,%25,%26,%27,%28,%29,%30,%31}, %32, %33, 0, 1, 1, %35, %34;"
   : "=f"(d[O+0]), "=f"(d[O+1]), "=f"(d[O+2]), "=f"(d[O+3]), "=f"(d[O+4]), "=f"(d[O+5]), "=f"(d[O+6]), "=f"(d[O+7]), "=f"(d[O+8]), "=f"(d[O+9]), "=f"(d[O+10]), "=f"(d[O+11]), "=f"(d[O+12]), "=f"(d[O+13]), "=f"(d[O+14]), "=f"(d[O+15]), "=f"(d[O+16]), "=f"(d[O+17]), "=f"(d[O+18]), "=f"(d[O+19]), "=f"(d[O+20]), "=f"(d[O+21]), "=f"(d[O+22]), "=f"(d[O+23]), "=f"(d[O+24]), "=f"(d[O+25]), "=f"(d[O+26]), "=f"(d[O+27]), "=f"(d[O+28]), "=f"(d[O+29]), "=f"(d[O+30]), "=f"(d[O+31])
   : "l"(da), "l"(db), "n"(TB & 1), "n"(TB >> 1));
  else asm volatile("{\n.reg .pred p;\nsetp.ne.b32 p, %36, 0;\nwgmma.mma_async.sync.aligned.m64n64k16.f32.bf16.bf16 {%0,%1,%2,%3,%4,%5,%6,%7,%8,%9,%10,%11,%12,%13,%14,%15,%16,%17,%18,%19,%20,%21,%22,%23,%24,%25,%26,%27,%28,%29,%30,%31}, %32, %33, p, 1, 1, %35, %34;\n}"
   : "+f"(d[O+0]), "+f"(d[O+1]), "+f"(d[O+2]), "+f"(d[O+3]), "+f"(d[O+4]), "+f"(d[O+5]), "+f"(d[O+6]), "+f"(d[O+7]), "+f"(d[O+8]), "+f"(d[O+9]), "+f"(d[O+10]), "+f"(d[O+11]), "+f"(d[O+12]), "+f"(d[O+13]), "+f"(d[O+14]), "+f"(d[O+15]), "+f"(d[O+16]), "+f"(d[O+17]), "+f"(d[O+18]), "+f"(d[O+19]), "+f"(d[O+20]), "+f"(d[O+21]), "+f"(d[O+22]), "+f"(d[O+23]), "+f"(d[O+24]), "+f"(d[O+25]), "+f"(d[O+26]), "+f"(d[O+27]), "+f"(d[O+28]), "+f"(d[O+29]), "+f"(d[O+30]), "+f"(d[O+31])
   : "l"(da), "l"(db), "n"(TB & 1), "n"(TB >> 1), "r"(sd));
}
template<int O,int TB,int ACC,int NN> __device__ __forceinline__ void mma_rs64(float (&d)[NN], uint32_t a0, uint32_t a1, uint32_t a2, uint32_t a3, uint64_t db, int sd = 0){
  if constexpr (ACC == 1) asm volatile("wgmma.mma_async.sync.aligned.m64n64k16.f32.bf16.bf16 {%0,%1,%2,%3,%4,%5,%6,%7,%8,%9,%10,%11,%12,%13,%14,%15,%16,%17,%18,%19,%20,%21,%22,%23,%24,%25,%26,%27,%28,%29,%30,%31}, {%32,%33,%34,%35}, %36, 1, 1, 1, %37;"
   : "+f"(d[O+0]), "+f"(d[O+1]), "+f"(d[O+2]), "+f"(d[O+3]), "+f"(d[O+4]), "+f"(d[O+5]), "+f"(d[O+6]), "+f"(d[O+7]), "+f"(d[O+8]), "+f"(d[O+9]), "+f"(d[O+10]), "+f"(d[O+11]), "+f"(d[O+12]), "+f"(d[O+13]), "+f"(d[O+14]), "+f"(d[O+15]), "+f"(d[O+16]), "+f"(d[O+17]), "+f"(d[O+18]), "+f"(d[O+19]), "+f"(d[O+20]), "+f"(d[O+21]), "+f"(d[O+22]), "+f"(d[O+23]), "+f"(d[O+24]), "+f"(d[O+25]), "+f"(d[O+26]), "+f"(d[O+27]), "+f"(d[O+28]), "+f"(d[O+29]), "+f"(d[O+30]), "+f"(d[O+31])
   : "r"(a0), "r"(a1), "r"(a2), "r"(a3), "l"(db), "n"(TB));
  else if constexpr (ACC == 0) asm volatile("wgmma.mma_async.sync.aligned.m64n64k16.f32.bf16.bf16 {%0,%1,%2,%3,%4,%5,%6,%7,%8,%9,%10,%11,%12,%13,%14,%15,%16,%17,%18,%19,%20,%21,%22,%23,%24,%25,%26,%27,%28,%29,%30,%31}, {%32,%33,%34,%35}, %36, 0, 1, 1, %37;"
   : "=f"(d[O+0]), "=f"(d[O+1]), "=f"(d[O+2]), "=f"(d[O+3]), "=f"(d[O+4]), "=f"(d[O+5]), "=f"(d[O+6]), "=f"(d[O+7]), "=f"(d[O+8]), "=f"(d[O+9]), "=f"(d[O+10]), "=f"(d[O+11]), "=f"(d[O+12]), "=f"(d[O+13]), "=f"(d[O+14]), "=f"(d[O+15]), "=f"(d[O+16]), "=f"(d[O+17]), "=f"(d[O+18]), "=f"(d[O+19]), "=f"(d[O+20]), "=f"(d[O+21]), "=f"(d[O+22]), "=f"(d[O+23]), "=f"(d[O+24]), "=f"(d[O+25]), "=f"(d[O+26]), "=f"(d[O+27]), "=f"(d[O+28]), "=f"(d[O+29]), "=f"(d[O+30]), "=f"(d[O+31])
   : "r"(a0), "r"(a1), "r"(a2), "r"(a3), "l"(db), "n"(TB));
  else asm volatile("{\n.reg .pred p;\nsetp.ne.b32 p, %38, 0;\nwgmma.mma_async.sync.aligned.m64n64k16.f32.bf16.bf16 {%0,%1,%2,%3,%4,%5,%6,%7,%8,%9,%10,%11,%12,%13,%14,%15,%16,%17,%18,%19,%20,%21,%22,%23,%24,%25,%26,%27,%28,%29,%30,%31}, {%32,%33,%34,%35}, %36, p, 1, 1, %37;\n}"
   : "+f"(d[O+0]), "+f"(d[O+1]), "+f"(d[O+2]), "+f"(d[O+3]), "+f"(d[O+4]), "+f"(d[O+5]), "+f"(d[O+6]), "+f"(d[O+7]), "+f"(d[O+8]), "+f"(d[O+9]), "+f"(d[O+10]), "+f"(d[O+11]), "+f"(d[O+12]), "+f"(d[O+13]), "+f"(d[O+14]), "+f"(d[O+15]), "+f"(d[O+16]), "+f"(d[O+17]), "+f"(d[O+18]), "+f"(d[O+19]), "+f"(d[O+20]), "+f"(d[O+21]), "+f"(d[O+22]), "+f"(d[O+23]), "+f"(d[O+24]), "+f"(d[O+25]), "+f"(d[O+26]), "+f"(d[O+27]), "+f"(d[O+28]), "+f"(d[O+29]), "+f"(d[O+30]), "+f"(d[O+31])
   : "r"(a0), "r"(a1), "r"(a2), "r"(a3), "l"(db), "n"(TB), "r"(sd));
}
template<int O,int TB,int ACC,int NN> __device__ __forceinline__ void mma_ss128(float (&d)[NN], uint64_t da, uint64_t db, int sd = 0){
  if constexpr (ACC == 1) asm volatile("wgmma.mma_async.sync.aligned.m64n128k16.f32.bf16.bf16 {%0,%1,%2,%3,%4,%5,%6,%7,%8,%9,%10,%11,%12,%13,%14,%15,%16,%17,%18,%19,%20,%21,%22,%23,%24,%25,%26,%27,%28,%29,%30,%31,%32,%33,%34,%35,%36,%37,%38,%39,%40,%41,%42,%43,%44,%45,%46,%47,%48,%49,%50,%51,%52,%53,%54,%55,%56,%57,%58,%59,%60,%61,%62,%63}, %64, %65, 1, 1, 1, %67, %66;"
   : "+f"(d[O+0]), "+f"(d[O+1]), "+f"(d[O+2]), "+f"(d[O+3]), "+f"(d[O+4]), "+f"(d[O+5]), "+f"(d[O+6]), "+f"(d[O+7]), "+f"(d[O+8]), "+f"(d[O+9]), "+f"(d[O+10]), "+f"(d[O+11]), "+f"(d[O+12]), "+f"(d[O+13]), "+f"(d[O+14]), "+f"(d[O+15]), "+f"(d[O+16]), "+f"(d[O+17]), "+f"(d[O+18]), "+f"(d[O+19]), "+f"(d[O+20]), "+f"(d[O+21]), "+f"(d[O+22]), "+f"(d[O+23]), "+f"(d[O+24]), "+f"(d[O+25]), "+f"(d[O+26]), "+f"(d[O+27]), "+f"(d[O+28]), "+f"(d[O+29]), "+f"(d[O+30]), "+f"(d[O+31]), "+f"(d[O+32]), "+f"(d[O+33]), "+f"(d[O+34]), "+f"(d[O+35]), "+f"(d[O+36]), "+f"(d[O+37]), "+f"(d[O+38]), "+f"(d[O+39]), "+f"(d[O+40]), "+f"(d[O+41]), "+f"(d[O+42]), "+f"(d[O+43]), "+f"(d[O+44]), "+f"(d[O+45]), "+f"(d[O+46]), "+f"(d[O+47]), "+f"(d[O+48]), "+f"(d[O+49]), "+f"(d[O+50]), "+f"(d[O+51]), "+f"(d[O+52]), "+f"(d[O+53]), "+f"(d[O+54]), "+f"(d[O+55]), "+f"(d[O+56]), "+f"(d[O+57]), "+f"(d[O+58]), "+f"(d[O+59]), "+f"(d[O+60]), "+f"(d[O+61]), "+f"(d[O+62]), "+f"(d[O+63])
   : "l"(da), "l"(db), "n"(TB & 1), "n"(TB >> 1));
  else if constexpr (ACC == 0) asm volatile("wgmma.mma_async.sync.aligned.m64n128k16.f32.bf16.bf16 {%0,%1,%2,%3,%4,%5,%6,%7,%8,%9,%10,%11,%12,%13,%14,%15,%16,%17,%18,%19,%20,%21,%22,%23,%24,%25,%26,%27,%28,%29,%30,%31,%32,%33,%34,%35,%36,%37,%38,%39,%40,%41,%42,%43,%44,%45,%46,%47,%48,%49,%50,%51,%52,%53,%54,%55,%56,%57,%58,%59,%60,%61,%62,%63}, %64, %65, 0, 1, 1, %67, %66;"
   : "=f"(d[O+0]), "=f"(d[O+1]), "=f"(d[O+2]), "=f"(d[O+3]), "=f"(d[O+4]), "=f"(d[O+5]), "=f"(d[O+6]), "=f"(d[O+7]), "=f"(d[O+8]), "=f"(d[O+9]), "=f"(d[O+10]), "=f"(d[O+11]), "=f"(d[O+12]), "=f"(d[O+13]), "=f"(d[O+14]), "=f"(d[O+15]), "=f"(d[O+16]), "=f"(d[O+17]), "=f"(d[O+18]), "=f"(d[O+19]), "=f"(d[O+20]), "=f"(d[O+21]), "=f"(d[O+22]), "=f"(d[O+23]), "=f"(d[O+24]), "=f"(d[O+25]), "=f"(d[O+26]), "=f"(d[O+27]), "=f"(d[O+28]), "=f"(d[O+29]), "=f"(d[O+30]), "=f"(d[O+31]), "=f"(d[O+32]), "=f"(d[O+33]), "=f"(d[O+34]), "=f"(d[O+35]), "=f"(d[O+36]), "=f"(d[O+37]), "=f"(d[O+38]), "=f"(d[O+39]), "=f"(d[O+40]), "=f"(d[O+41]), "=f"(d[O+42]), "=f"(d[O+43]), "=f"(d[O+44]), "=f"(d[O+45]), "=f"(d[O+46]), "=f"(d[O+47]), "=f"(d[O+48]), "=f"(d[O+49]), "=f"(d[O+50]), "=f"(d[O+51]), "=f"(d[O+52]), "=f"(d[O+53]), "=f"(d[O+54]), "=f"(d[O+55]), "=f"(d[O+56]), "=f"(d[O+57]), "=f"(d[O+58]), "=f"(d[O+59]), "=f"(d[O+60]), "=f"(d[O+61]), "=f"(d[O+62]), "=f"(d[O+63])
   : "l"(da), "l"(db), "n"(TB & 1), "n"(TB >> 1));
  else asm volatile("{\n.reg .pred p;\nsetp.ne.b32 p, %68, 0;\nwgmma.mma_async.sync.aligned.m64n128k16.f32.bf16.bf16 {%0,%1,%2,%3,%4,%5,%6,%7,%8,%9,%10,%11,%12,%13,%14,%15,%16,%17,%18,%19,%20,%21,%22,%23,%24,%25,%26,%27,%28,%29,%30,%31,%32,%33,%34,%35,%36,%37,%38,%39,%40,%41,%42,%43,%44,%45,%46,%47,%48,%49,%50,%51,%52,%53,%54,%55,%56,%57,%58,%59,%60,%61,%62,%63}, %64, %65, p, 1, 1, %67, %66;\n}"
   : "+f"(d[O+0]), "+f"(d[O+1]), "+f"(d[O+2]), "+f"(d[O+3]), "+f"(d[O+4]), "+f"(d[O+5]), "+f"(d[O+6]), "+f"(d[O+7]), "+f"(d[O+8]), "+f"(d[O+9]), "+f"(d[O+10]), "+f"(d[O+11]), "+f"(d[O+12]), "+f"(d[O+13]), "+f"(d[O+14]), "+f"(d[O+15]), "+f"(d[O+16]), "+f"(d[O+17]), "+f"(d[O+18]), "+f"(d[O+19]), "+f"(d[O+20]), "+f"(d[O+21]), "+f"(d[O+22]), "+f"(d[O+23]), "+f"(d[O+24]), "+f"(d[O+25]), "+f"(d[O+26]), "+f"(d[O+27]), "+f"(d[O+28]), "+f"(d[O+29]), "+f"(d[O+30]), "+f"(d[O+31]), "+f"(d[O+32]), "+f"(d[O+33]), "+f"(d[O+34]), "+f"(d[O+35]), "+f"(d[O+36]), "+f"(d[O+37]), "+f"(d[O+38]), "+f"(d[O+39]), "+f"(d[O+40]), "+f"(d[O+41]), "+f"(d[O+42]), "+f"(d[O+43]), "+f"(d[O+44]), "+f"(d[O+45]), "+f"(d[O+46]), "+f"(d[O+47]), "+f"(d[O+48]), "+f"(d[O+49]), "+f"(d[O+50]), "+f"(d[O+51]), "+f"(d[O+52]), "+f"(d[O+53]), "+f"(d[O+54]), "+f"(d[O+55]), "+f"(d[O+56]), "+f"(d[O+57]), "+f"(d[O+58]), "+f"(d[O+59]), "+f"(d[O+60]), "+f"(d[O+61]), "+f"(d[O+62]), "+f"(d[O+63])
   : "l"(da), "l"(db), "n"(TB & 1), "n"(TB >> 1), "r"(sd));
}
template<int O,int TB,int ACC,int NN> __device__ __forceinline__ void mma_rs128(float (&d)[NN], uint32_t a0, uint32_t a1, uint32_t a2, uint32_t a3, uint64_t db, int sd = 0){
  if constexpr (ACC == 1) asm volatile("wgmma.mma_async.sync.aligned.m64n128k16.f32.bf16.bf16 {%0,%1,%2,%3,%4,%5,%6,%7,%8,%9,%10,%11,%12,%13,%14,%15,%16,%17,%18,%19,%20,%21,%22,%23,%24,%25,%26,%27,%28,%29,%30,%31,%32,%33,%34,%35,%36,%37,%38,%39,%40,%41,%42,%43,%44,%45,%46,%47,%48,%49,%50,%51,%52,%53,%54,%55,%56,%57,%58,%59,%60,%61,%62,%63}, {%64,%65,%66,%67}, %68, 1, 1, 1, %69;"
   : "+f"(d[O+0]), "+f"(d[O+1]), "+f"(d[O+2]), "+f"(d[O+3]), "+f"(d[O+4]), "+f"(d[O+5]), "+f"(d[O+6]), "+f"(d[O+7]), "+f"(d[O+8]), "+f"(d[O+9]), "+f"(d[O+10]), "+f"(d[O+11]), "+f"(d[O+12]), "+f"(d[O+13]), "+f"(d[O+14]), "+f"(d[O+15]), "+f"(d[O+16]), "+f"(d[O+17]), "+f"(d[O+18]), "+f"(d[O+19]), "+f"(d[O+20]), "+f"(d[O+21]), "+f"(d[O+22]), "+f"(d[O+23]), "+f"(d[O+24]), "+f"(d[O+25]), "+f"(d[O+26]), "+f"(d[O+27]), "+f"(d[O+28]), "+f"(d[O+29]), "+f"(d[O+30]), "+f"(d[O+31]), "+f"(d[O+32]), "+f"(d[O+33]), "+f"(d[O+34]), "+f"(d[O+35]), "+f"(d[O+36]), "+f"(d[O+37]), "+f"(d[O+38]), "+f"(d[O+39]), "+f"(d[O+40]), "+f"(d[O+41]), "+f"(d[O+42]), "+f"(d[O+43]), "+f"(d[O+44]), "+f"(d[O+45]), "+f"(d[O+46]), "+f"(d[O+47]), "+f"(d[O+48]), "+f"(d[O+49]), "+f"(d[O+50]), "+f"(d[O+51]), "+f"(d[O+52]), "+f"(d[O+53]), "+f"(d[O+54]), "+f"(d[O+55]), "+f"(d[O+56]), "+f"(d[O+57]), "+f"(d[O+58]), "+f"(d[O+59]), "+f"(d[O+60]), "+f"(d[O+61]), "+f"(d[O+62]), "+f"(d[O+63])
   : "r"(a0), "r"(a1), "r"(a2), "r"(a3), "l"(db), "n"(TB));
  else if constexpr (ACC == 0) asm volatile("wgmma.mma_async.sync.aligned.m64n128k16.f32.bf16.bf16 {%0,%1,%2,%3,%4,%5,%6,%7,%8,%9,%10,%11,%12,%13,%14,%15,%16,%17,%18,%19,%20,%21,%22,%23,%24,%25,%26,%27,%28,%29,%30,%31,%32,%33,%34,%35,%36,%37,%38,%39,%40,%41,%42,%43,%44,%45,%46,%47,%48,%49,%50,%51,%52,%53,%54,%55,%56,%57,%58,%59,%60,%61,%62,%63}, {%64,%65,%66,%67}, %68, 0, 1, 1, %69;"
   : "=f"(d[O+0]), "=f"(d[O+1]), "=f"(d[O+2]), "=f"(d[O+3]), "=f"(d[O+4]), "=f"(d[O+5]), "=f"(d[O+6]), "=f"(d[O+7]), "=f"(d[O+8]), "=f"(d[O+9]), "=f"(d[O+10]), "=f"(d[O+11]), "=f"(d[O+12]), "=f"(d[O+13]), "=f"(d[O+14]), "=f"(d[O+15]), "=f"(d[O+16]), "=f"(d[O+17]), "=f"(d[O+18]), "=f"(d[O+19]), "=f"(d[O+20]), "=f"(d[O+21]), "=f"(d[O+22]), "=f"(d[O+23]), "=f"(d[O+24]), "=f"(d[O+25]), "=f"(d[O+26]), "=f"(d[O+27]), "=f"(d[O+28]), "=f"(d[O+29]), "=f"(d[O+30]), "=f"(d[O+31]), "=f"(d[O+32]), "=f"(d[O+33]), "=f"(d[O+34]), "=f"(d[O+35]), "=f"(d[O+36]), "=f"(d[O+37]), "=f"(d[O+38]), "=f"(d[O+39]), "=f"(d[O+40]), "=f"(d[O+41]), "=f"(d[O+42]), "=f"(d[O+43]), "=f"(d[O+44]), "=f"(d[O+45]), "=f"(d[O+46]), "=f"(d[O+47]), "=f"(d[O+48]), "=f"(d[O+49]), "=f"(d[O+50]), "=f"(d[O+51]), "=f"(d[O+52]), "=f"(d[O+53]), "=f"(d[O+54]), "=f"(d[O+55]), "=f"(d[O+56]), "=f"(d[O+57]), "=f"(d[O+58]), "=f"(d[O+59]), "=f"(d[O+60]), "=f"(d[O+61]), "=f"(d[O+62]), "=f"(d[O+63])
   : "r"(a0), "r"(a1), "r"(a2), "r"(a3), "l"(db), "n"(TB));
  else asm volatile("{\n.reg .pred p;\nsetp.ne.b32 p, %70, 0;\nwgmma.mma_async.sync.aligned.m64n128k16.f32.bf16.bf16 {%0,%1,%2,%3,%4,%5,%6,%7,%8,%9,%10,%11,%12,%13,%14,%15,%16,%17,%18,%19,%20,%21,%22,%23,%24,%25,%26,%27,%28,%29,%30,%31,%32,%33,%34,%35,%36,%37,%38,%39,%40,%41,%42,%43,%44,%45,%46,%47,%48,%49,%50,%51,%52,%53,%54,%55,%56,%57,%58,%59,%60,%61,%62,%63}, {%64,%65,%66,%67}, %68, p, 1, 1, %69;\n}"
   : "+f"(d[O+0]), "+f"(d[O+1]), "+f"(d[O+2]), "+f"(d[O+3]), "+f"(d[O+4]), "+f"(d[O+5]), "+f"(d[O+6]), "+f"(d[O+7]), "+f"(d[O+8]), "+f"(d[O+9]), "+f"(d[O+10]), "+f"(d[O+11]), "+f"(d[O+12]), "+f"(d[O+13]), "+f"(d[O+14]), "+f"(d[O+15]), "+f"(d[O+16]), "+f"(d[O+17]), "+f"(d[O+18]), "+f"(d[O+19]), "+f"(d[O+20]), "+f"(d[O+21]), "+f"(d[O+22]), "+f"(d[O+23]), "+f"(d[O+24]), "+f"(d[O+25]), "+f"(d[O+26]), "+f"(d[O+27]), "+f"(d[O+28]), "+f"(d[O+29]), "+f"(d[O+30]), "+f"(d[O+31]), "+f"(d[O+32]), "+f"(d[O+33]), "+f"(d[O+34]), "+f"(d[O+35]), "+f"(d[O+36]), "+f"(d[O+37]), "+f"(d[O+38]), "+f"(d[O+39]), "+f"(d[O+40]), "+f"(d[O+41]), "+f"(d[O+42]), "+f"(d[O+43]), "+f"(d[O+44]), "+f"(d[O+45]), "+f"(d[O+46]), "+f"(d[O+47]), "+f"(d[O+48]), "+f"(d[O+49]), "+f"(d[O+50]), "+f"(d[O+51]), "+f"(d[O+52]), "+f"(d[O+53]), "+f"(d[O+54]), "+f"(d[O+55]), "+f"(d[O+56]), "+f"(d[O+57]), "+f"(d[O+58]), "+f"(d[O+59]), "+f"(d[O+60]), "+f"(d[O+61]), "+f"(d[O+62]), "+f"(d[O+63])
   : "r"(a0), "r"(a1), "r"(a2), "r"(a3), "l"(db), "n"(TB), "r"(sd));
}

#define NEARLY 0
#define XAHEAD 3
#define HEADN 6
#define WBATCH 1
#define WB 8
#define WSLEEP 20
#define XSPREAD 4
#define NOSEND 0
#define MSPLIT 2
#define PFALL 1
#define L2PF 0
#define STAG 0
#define EPF 2
#define XNB 2
#define FNB 0
#define GNB 0
#define TH 4
#define PF0 4
#define FSPLIT 1
#define MGLU 1
#define SPC 2
#define TL 14
#define GKB 4
#define T0A 7
#define T0B 11
#define TGATE 1
#define ZLATE 0
#define EARLYADD 0
#define OA 3
#define OB 11
#define EB 8
#define PROMO 2
#define SPACE 100
#define WPF 1
#define WAFTER 7
#define WPACE 0
#define GATE_AT 4
#define TPACE 40
#define PFMODE 0
#define MAPMODE 1
template <int V> struct IC { static constexpr int value = V; };
struct Maps { CUtensorMap x, ft, g64, u64, e, wr, wi, xs, ts, t, g32, u32, d224, fg; };

constexpr int NCTA = 130;
constexpr int U = 16384;
constexpr int TB = 36864;
constexpr int OFF_RING = 8 * U, OFF_Z = 12 * U, OFF_XB = 12 * U, OFF_T = 13 * U, OFF_D = OFF_T;
constexpr int OFF_BAR = 14 * U, OFF_SP = OFF_BAR + 512, OFF_G = OFF_SP + 1024 + 128;
constexpr int SMEM_BYTES = OFF_G + 512;
constexpr int B_FX = 0, B_FA = 8, B_FT = 12, B_Z = 16, B_W = 24, B_HX = 25, B_TL = 26, B_HP = 27, B_WR = 31;
constexpr int B_EA = 36, B_ET = 40, B_PZ = 44, B_RDY = 46, B_FE = 47;
constexpr int B_T = 51, B_XS = 52, B_G = 54, B_RD0 = 55, NBAR = 56;
__device__ __forceinline__ int srow(int rb, int r) { return 2 * rb + (r >> 6) + 32 * (r & 7) + 256 * ((r >> 4) & 3) + 1024 * ((r >> 3) & 1); }
__host__ __device__ constexpr int rslot(int n) { return n & 3; }
__host__ __device__ constexpr int rpar(int n) { return (n >> 2) & 1; }

__global__ void __cluster_dims__(2, 1, 1) __launch_bounds__(512, 1)
fused_kernel(Work* __restrict__ ws, const uint16_t* __restrict__ dtab, const __nv_bfloat16* __restrict__ w_r, const __nv_bfloat16* __restrict__ w_i,
             const __nv_bfloat16* __restrict__ gate_w, const __nv_bfloat16* __restrict__ x, __nv_bfloat16* __restrict__ out,
             const __grid_constant__ Maps maps) {
  extern __shared__ __align__(1024) uint8_t smem[];
  if (threadIdx.x < 32 && elect_one()) {
#pragma unroll
    for (int i = 0; i < PF0; i++) asm volatile("prefetch.tensormap [%0];" ::"l"((const char*)&maps + i * 128) : "memory");
  }
  const uint32_t sb = smem_u32(smem);
  const uint32_t bars = sb + OFF_BAR;
  const int tid = threadIdx.x, lane = tid & 31;
  const int warp = __shfl_sync(0xffffffffu, tid >> 5, 0);
  const bool helper = blockIdx.x >= 128;
  const int cl = (blockIdx.x >> 1) & 63, rank = blockIdx.x & 1;
  const int q4 = (cl & 1) | ((cl >> 2) & 2), rb = ((cl >> 1) & 3) | ((cl >> 4) << 2);
  const int j = 2 * q4 + rank;
  const int f_full = 448 * q4 + (rank ? 256 : 0);
  const int f_half = 448 * q4 + (rank ? 224 : 192);

  if (tid == 64) { PROF_EV(0); PROF_CK(40); }
  if (warp < 8) {
    if (!helper && tid < 32) {
      const int r = 16 * j + (tid & 15);
      asm volatile("prefetch.global.L2 [%0];" ::"l"(x + (size_t)srow(rb, r) * 512 + 64 * (tid >> 4)));
    }
    asm volatile("barrier.cluster.arrive.relaxed.aligned;" ::: "memory");
    asm volatile("setmaxnreg.inc.sync.aligned.u32 192;");
    if (!helper) {
      const int wg = warp >> 2, w = warp & 3, g = lane >> 2;
      const bool elect = (tid & 127) == 0;
      float cX[32], cD[64], cA[64], cB[64], cC[64], ci[64], ct[64];
      const int zero = blockIdx.x >> 16;
      uint32_t h[56], yf[16];
      const uint32_t d0 = (sb & 0x3FFFF) >> 4;
      const uint32_t dK = d0 | (1u << 16), dN = d0 | (512u << 16);
      const uint32_t dX = dK + wg * 512;
      constexpr uint32_t RING = OFF_RING >> 4;
      auto waitA = [&](int n) { mbar_wait(bars + 8 * (B_FA + rslot(n)), rpar(n)); };
      auto freeA = [&](int n) { mbar_arrive_if(elect, bars + 8 * (B_EA + rslot(n))); };
      auto nop = [] {};

      asm volatile("bar.sync 0, 384;" ::: "memory");
#pragma unroll 1
      for (int i = 0; i < 4; i++) {
        const uint64_t dx = d128(dX + i * 2048), df = d128(dK + (OFF_XB >> 4) + (i & 1) * 1024);
        mbar_wait(bars + 8 * (B_FX + 2 * i), 0);
        wg_fence();
        mma_ss64<0, 0, 2>(cX, df, dx, i);
        mma_ss64<0, 0, 1>(cX, df + 2, dx + 2);
        wg_commit(); wg_wait<1>();
        mbar_arrive_if(elect && i, bars + 8 * (B_EA + rslot(i - 1)));
        mma_ss64<0, 0, 1>(cX, df + 4, dx + 4);
        mma_ss64<0, 0, 1>(cX, df + 6, dx + 6);
        if (i == 0 && tid == 0) PROF_EV(1);
        mbar_wait(bars + 8 * (B_FX + 2 * i + 1), 0);
        wg_fence();
#pragma unroll
        for (int k = 0; k < 4; k++) mma_ss64<0, 0, 1>(cX, df + (512 + k * 2), dx + (1024 + k * 2));
        wg_commit();
        waitA(i);
        wg_fence();
        const uint64_t da = d128(dX + i * 1024), db = d128(dN + RING + i * 1024);
        mma_ss128<0, 1, 2>(cA, da, db, i);
        wg_commit(); wg_wait<1>();
        mbar_arrive_if(elect, bars + 8 * (B_FE + i));
#pragma unroll
        for (int k = 1; k < 4; k++) mma_ss128<0, 1, 1>(cA, da + k * 2, db + k * 128);
        wg_commit();
      }
      fence_regs<0, 32>(cX);
#pragma unroll
      for (int e = 0; e < 8; e++) {
        const int o = 8 * (e >> 1) + 2 * (e & 1);
        yf[e] = pack_pin(cX[o] + cX[o + 4], cX[o + 1] + cX[o + 5]); yf[8 + e] = pack_pin(cX[o] - cX[o + 4], cX[o + 1] - cX[o + 5]);
      }
      if (tid == 0) { PROF_EV(2); PROF_CK(42); }
      {
        waitA(4);
        const uint64_t de = d128(dN + RING + wg * 512);
        wg_fence();
        mma_rs64<0, 1, 0>(cD, yf[0], yf[1], yf[2], yf[3], de);
        mma_rs64<32, 1, 0>(cD, yf[8], yf[9], yf[10], yf[11], de + 256);
        wg_commit();
        wg_wait<1>();
        freeA(3);
        mma_rs64<0, 1, 1>(cD, yf[4], yf[5], yf[6], yf[7], de + 128);
        mma_rs64<32, 1, 1>(cD, yf[12], yf[13], yf[14], yf[15], de + 384);
        wg_commit();
      }
      bool rel = false;
      auto acquire = [&](int n) {
        rel = elect;
        if (!mbar_try(bars + 8 * (B_FA + rslot(n)), rpar(n))) { wg_wait<0>(); freeA(n - 1); rel = false; waitA(n); }
      };
      auto freeP = [&](int n) { mbar_arrive_if(rel, bars + 8 * (B_EA + rslot(n - 1))); };
      auto ffn_step = [&](auto first, auto split, float (&acc)[64], int n, int kb, auto done, auto work) {
        constexpr int SPLIT = decltype(split)::value;
        acquire(n);
        wg_fence();
        const uint64_t dx = d128(dX + kb * 1024), db = d128(dN + RING + rslot(n) * 1024);
        mma_ss128<0, 1, decltype(first)::value>(acc, dx, db, kb);
#pragma unroll
        for (int k = 1; k < SPLIT; k++) mma_ss128<0, 1, 1>(acc, dx + k * 2, db + k * 128);
        wg_commit();
        work();
        wg_wait<1>();
        freeP(n);
        done();
        if (SPLIT < 4) {
          wg_fence();
#pragma unroll
          for (int k = SPLIT; k < 4; k++) mma_ss128<0, 1, 1>(acc, dx + k * 2, db + k * 128);
          wg_commit();
        }
      };
      {
        const int s0 = 2 * rb + wg, kr = 2 * ((s0 & 1) | ((s0 & 4) >> 1));
        const int m = lane >> 3, r = lane & 7;
        const uint32_t a0 = sb + OFF_XB + wg * 8192 + ((2 * (m >> 1) + (r >> 2)) * 2 + (w & 1)) * 256 + (m & 1) * 128 + (((2 * (r & 3) + ((w >> 1) ^ (r >> 2))) ^ (kr + (m & 1))) << 4);
        ffn_step(IC<1>(), IC<4>(), cA, 5, 4, [&] { fence_regs<0, 64>(cD); }, [&] { mbar_wait(bars + 8 * (B_FE + 2), 0); });
        auto stage = [&](int i) {
          const int o = 32 * (i >> 1) + 8 * (i & 1);
          stsm4t(a0 + i * 2048, pack_bf16(cD[o] - cD[o + 18], cD[o + 1] - cD[o + 19]), pack_bf16(cD[o + 16] + cD[o + 2], cD[o + 17] + cD[o + 3]),
                 pack_bf16(cD[o + 4] - cD[o + 22], cD[o + 5] - cD[o + 23]), pack_bf16(cD[o + 20] + cD[o + 6], cD[o + 21] + cD[o + 7]));
          if (j == 0 && w == 0) {
            const uint32_t a1 = r ? sb + OFF_SP + 1024 : sb + OFF_SP + wg * 512 + (m & 1) * 256 + (m >> 1) * 128;
#pragma unroll
            for (int n = 0; n < 2; n++)
              asm volatile("stmatrix.sync.aligned.m8n8.x4.shared.b16 [%0], {%1,%2,%3,%4};" ::"r"(a1 + (((2 * i + n) ^ (kr + (m >> 1)) ^ r) << 4)),
                           "r"(pack_bf16(cD[o + 4 * n], cD[o + 4 * n + 1])), "r"(pack_bf16(cD[o + 4 * n + 2], cD[o + 4 * n + 3])),
                           "r"(pack_bf16(cD[o + 16 + 4 * n], cD[o + 17 + 4 * n])), "r"(pack_bf16(cD[o + 18 + 4 * n], cD[o + 19 + 4 * n])) : "memory");
          }
        };
        auto publish = [&] {
          asm volatile("fence.proxy.async.shared::cta;" ::: "memory");
          __syncwarp();
          mbar_arrive_if(lane == 0, bars + 8 * (B_XS + wg));
          if (tid == 0) PROF_EV(3);
        };
        stage(0);
        ffn_step(IC<1>(), IC<FSPLIT>(), cA, 6, 5, nop, nop);
        stage(1);
        ffn_step(IC<1>(), IC<FSPLIT>(), cA, 7, 6, nop, nop);
        stage(2);
        ffn_step(IC<1>(), IC<2>(), cA, 8, 7, [&] { stage(3); }, nop);
        publish();
      }
      uint32_t gb0 = 0, gb1 = 0;
      uint32_t ob[2] = {0, 0};
      auto glu = [&](auto& acc, int half, int ho, int i0, int i1) {
#pragma unroll
        for (int i = i0; i < i1; i++)
          asm volatile("{\n.reg .b32 a, b;\ncvt.rn.relu.bf16x2.f32 a, %2, %1;\ncvt.rn.bf16x2.f32 b, %4, %3;\nmul.rn.bf16x2 a, a, b;\nmul.rn.bf16x2 %0, a, %5;\n}"
                       : "=r"(h[ho + i]) : "f"(acc[2 * i]), "f"(acc[2 * i + 1]), "f"(acc[half + 2 * i]), "f"(acc[half + 1 + 2 * i]), "r"(ob[i & 1]) : "memory");
      };
      ffn_step(IC<0>(), IC<1>(), cB, 9, 0, nop, nop);
#pragma unroll 1
      for (int kb = 1; kb < 8; kb++)
        ffn_step(IC<1>(), IC<FSPLIT>(), cB, 9 + kb, kb, nop, [&] {
          if (kb == GKB) {
            mbar_wait(bars + 8 * B_G, 0);
            asm volatile("ld.shared.u32 %0, [%2];\nld.shared.u32 %1, [%2+32];" : "=r"(gb0), "=r"(gb1) : "r"(sb + OFF_G + (wg * 64 + w * 16 + g) * 4) : "memory");
          } else if (kb == 5 + 2 * wg) {
            ob[0] = pack_bf16(1.0f - bf_hi(gb0), 1.0f - bf_hi(gb0)); ob[1] = pack_bf16(1.0f - bf_hi(gb1), 1.0f - bf_hi(gb1));
            glu(cA, 32, 0, 0, 16);
          }
        });
      const uint32_t tag = gb0 & 1;
      const float g0 = bf_hi(gb0), g1 = bf_hi(gb1);
      if (tid == 0) { PROF_EV(4); PROF_CK(43); }
      auto m_step = [&](auto first, int i) {
        acquire(17 + i);
        wg_fence();
        const uint64_t dx = d128(dX + i * 2048), dm = d64(dN + RING + rslot(17 + i) * 1024);
        mma_ss64<0, 1, decltype(first)::value>(ct, dx, dm);
#pragma unroll
        for (int k = 1; k < MSPLIT; k++) mma_ss64<0, 1, 1>(ct, dx + ((k >> 2) * 1024 + (k & 3) * 2), dm + k * 64);
        wg_commit();
        wg_wait<1>();
        freeP(17 + i);
        wg_fence();
#pragma unroll
        for (int k = MSPLIT; k < 8; k++) mma_ss64<0, 1, 1>(ct, dx + ((k >> 2) * 1024 + (k & 3) * 2), dm + k * 64);
        wg_commit();
      };
      m_step(IC<0>(), 0);
#pragma unroll 1
      for (int i = 1; i < 5; i++) {
        if (i == 1 + 2 * wg) glu(cB, 32, 16, 0, 16);
        if (i < 4) m_step(IC<1>(), i);
      }
      if (tid == 0) { PROF_EV(5); PROF_CK(44); }
      ffn_step(IC<0>(), IC<1>(), cC, 21, 0, nop, nop);
#pragma unroll 1
      for (int kb = 1; kb < 8; kb++)
        ffn_step(IC<1>(), IC<FSPLIT>(), cC, 21 + kb, kb, [&] { mbar_arrive_if(elect && !(kb & 1), bars + 8 * (B_ET + (kb >> 1) - 1)); }, [&] {
          if (kb == 1 + wg) glu(ct, 16, 48, 0, 8);
        });

      auto twait = [&](uint32_t bar, uint32_t par, int) { mbar_wait(bar, par); };
      const int fo = warp * 128 + lane;
      auto fetch = [&](uint4 (&pv)[4], int z) {
        twait(bars + 8 * (z < 4 ? B_Z + 2 * z + wg : z < 6 ? B_HP + z - 4 : B_HP + 2 + wg), 0, 8 + z);
        const uint8_t* src = smem + (z < 4 ? OFF_Z - z * U : z == 4 ? OFF_T : (z - 5) * U) + fo * 16;
#pragma unroll
        for (int i = 0; i < 4; i++) pv[i] = *(const uint4*)(src + i * 512);
      };
      const uint32_t peerZ = mapa(sb + OFF_Z + fo * 16, rank ^ 1), peerB = mapa(bars + 8 * (B_Z + wg), rank ^ 1);
      auto tile_mma = [&](auto off, int t, int k0, int k1, bool fresh = false) {
        constexpr int O = decltype(off)::value;
        const uint64_t db = d128(dN + (t & 3) * (TB >> 4)), dw = db + rank * 256, dm = db + (rank ? 0 : 1536);
#pragma unroll
        for (int k = k0; k < k1; k++) {
          if (k == 0 && O == 0) mma_rs64<O, 1, 2>(ct, h[0], h[1], h[2], h[3], dw, zero);
          else if (k < 14) mma_rs64<O, 1, 1>(ct, h[4 * k], h[4 * k + 1], h[4 * k + 2], h[4 * k + 3], k < 12 ? dw + k * 128 : dm + (k - 12) * 128);
          else if (k == 14 && fresh) mma_rs64<O, 1, 0>(ct, yf[0], yf[1], yf[2], yf[3], db + k * 128);
          else if (k == 14) mma_rs64<O, 1, 2>(ct, yf[0], yf[1], yf[2], yf[3], db + k * 128, zero);
          else mma_rs64<O, 1, 1>(ct, yf[4 * k - 56], yf[4 * k - 55], yf[4 * k - 54], yf[4 * k - 53], db + k * 128);
        }
      };
      uint4 pv[4];
      const uint32_t sgn = rank ? 0x80008000u : 0u;
      auto even_end = [&](int t, int k0, bool fresh) {
        wg_fence();
        tile_mma(IC<32>(), t, 14, 18, fresh);
        wg_commit();
        tile_mma(IC<0>(), t, k0, 14);
        wg_commit();
        wg_wait<1>();
        fence_regs<32, 32>(ct);
#pragma unroll
        for (int i = 0; i < 4; i++)
          pv[i] = make_uint4(pack_pin(ct[32 + 8 * i], ct[33 + 8 * i]) ^ sgn, pack_pin(ct[34 + 8 * i], ct[35 + 8 * i]) ^ sgn,
                             pack_pin(ct[36 + 8 * i], ct[37 + 8 * i]) ^ sgn, pack_pin(ct[38 + 8 * i], ct[39 + 8 * i]) ^ sgn);
      };
      auto odd_head = [&](int t) {
        twait(bars + 8 * (B_FT + (t & 3)), t >> 2, t);
        wg_fence();
        tile_mma(IC<32>(), t, 0, OA);
        wg_commit();
        if (t < 4) twait(bars + 8 * (t == 1 ? B_RD0 : B_RDY), 0, 14 + t);
        wg_wait<1>();
        mbar_arrive_if(elect && t < 6, bars + 8 * (B_ET + t - 1));
        fence_regs<0, 32>(ct);
        wg_fence();
#pragma unroll
        for (int i = 0; i < 4; i++) {
          asm volatile("st.async.weak.shared::cluster.mbarrier::complete_tx::bytes.v4.b32 [%0], {%2,%3,%4,%5}, [%1];" ::"r"(peerZ - (t >> 1) * U + i * 512),
                       "r"(peerB + 16 * (t >> 1)), "r"(add_bf2(pv[i].x, pack_bf16(ct[8 * i], ct[8 * i + 1]))), "r"(add_bf2(pv[i].y, pack_bf16(ct[8 * i + 2], ct[8 * i + 3]))),
                       "r"(add_bf2(pv[i].z, pack_bf16(ct[8 * i + 4], ct[8 * i + 5]))), "r"(add_bf2(pv[i].w, pack_bf16(ct[8 * i + 6], ct[8 * i + 7]))) : "memory");
          tile_mma(IC<32>(), t, OA + i, OA + i + 1);
        }
        wg_commit();
      };
      asm volatile("barrier.cluster.wait.aligned;" ::: "memory");
      twait(bars + 8 * B_FT, 0, 0);
      wg_fence();
      tile_mma(IC<0>(), 0, 0, T0A);
      wg_commit();
      waitA(29);
      wg_wait<1>();
      mbar_arrive_if(elect, bars + 8 * (B_ET + 3));
      glu(cC, 32, 32, 0, 16);
      if (tid == 0) PROF_EV(6);
      if (tid == 128) PROF_EV(27);
      mbar_wait(bars + 8 * (j == 0 ? B_T : B_TL), 0);
      if (tid == 0) { PROF_EV(7); PROF_CK(45); }
      wg_fence();
      {
        const uint64_t dt = d128(dN + (OFF_T >> 4) + wg * 512), de = d128(dK + RING + 1024 + wg * 512);
        mma_ss64<0, 1, 0>(ci, de, dt);
        mma_ss64<32, 1, 0>(ci, de + 4, dt + 256);
        mma_ss64<0, 1, 1>(ci, de + 2, dt + 128);
        mma_ss64<32, 1, 1>(ci, de + 6, dt + 384);
        wg_commit();
      }
      tile_mma(IC<0>(), 0, T0A, T0B);
      wg_commit();
      wg_wait<1>();
      if (elect) asm volatile("mbarrier.arrive.shared::cluster.b64 _, [%0];" ::"r"(mapa(bars + 8 * B_RDY, rank ^ 1)) : "memory");
      mbar_arrive_if(elect, bars + 8 * (B_PZ + 1));
      fence_regs<0, 64>(ci);
#pragma unroll
      for (int n = 0; n < 8; n++) {
        const float s0 = g0 * (2.0f / (2048.0f * 512.0f)), s1 = g1 * (2.0f / (2048.0f * 512.0f));
        float u[4];
#pragma unroll
        for (int e = 0; e < 4; e++) {
          const int o = 32 * (e >> 1) + 4 * n + (e & 1);
          u[e] = (n & 1) ? ci[o] - ci[o - 2] : ci[o] + ci[o + 6];
        }
        yf[2 * n] = pack_pin((u[0] + u[2]) * s0, (u[1] + u[3]) * s0); yf[2 * n + 1] = pack_pin((u[0] - u[2]) * s1, (u[1] - u[3]) * s1);
      }
      even_end(0, T0B, true);
      if (tid == 0) PROF_EV(8);
      if (tid == 128) PROF_EV(28);
#pragma unroll 1
      for (int t = 1; t < 7; t += 2) {
        odd_head(t);
        wg_fence();
        tile_mma(IC<32>(), t, OA + 4, 14);
        wg_commit();
        const int zo = t >> 1, owner = rb * 8 + 2 * ((q4 + zo + 1) & 3) + rank;
        uint4* dst = ws->part + (size_t)(owner * 3 + zo) * 1024 + fo;
        auto send = [&] {
          fence_regs<32, 32>(ct);
#pragma unroll
          for (int i = 0; i < 4; i++)
            asm volatile("st.relaxed.gpu.global.v4.u32 [%0], {%1,%2,%3,%4};" ::"l"(dst + i * 32),
                         "r"((add_bf2(pv[i].x, pack_bf16(ct[32 + 8 * i], ct[33 + 8 * i])) & ~1u) | tag), "r"(add_bf2(pv[i].y, pack_bf16(ct[34 + 8 * i], ct[35 + 8 * i]))),
                         "r"(add_bf2(pv[i].z, pack_bf16(ct[36 + 8 * i], ct[37 + 8 * i]))), "r"(add_bf2(pv[i].w, pack_bf16(ct[38 + 8 * i], ct[39 + 8 * i]))) : "memory");
          hint_add_if(lane == 0, &ws->cntP[32 * owner + 8 * (zo + (zo == 2 ? wg : 0))]);
        };
        if (t == 5) fetch(pv, 2);
        twait(bars + 8 * (B_FT + ((t + 1) & 3)), (t + 1) >> 2, t + 1);
        wg_fence();
        tile_mma(IC<0>(), t + 1, 0, TH);
        wg_commit();
        wg_wait<1>();
        mbar_arrive_if(elect && t < 5, bars + 8 * (B_ET + t));
        if (t == 5) send(); else fetch(pv, zo);
        wg_fence();
        tile_mma(IC<0>(), t + 1, TH, EB);
        wg_commit();
        if (t != 5) send();
        even_end(t + 1, EB, false);
      }
      {
        uint4 p1[4], p2[4];
        auto acc4 = [&](uint4 (&d)[4], const uint4 (&a)[4]) {
#pragma unroll
          for (int i = 0; i < 4; i++) { d[i].x = add_bf2(d[i].x, a[i].x); d[i].y = add_bf2(d[i].y, a[i].y); d[i].z = add_bf2(d[i].z, a[i].z); d[i].w = add_bf2(d[i].w, a[i].w); }
        };
        auto add32 = [&](const uint4 (&a)[4]) {
#pragma unroll
          for (int i = 0; i < 4; i++) {
            const uint32_t u[4] = {a[i].x, a[i].y, a[i].z, a[i].w};
#pragma unroll
            for (int e = 0; e < 4; e++) { ct[32 + 8 * i + 2 * e] += bf_lo(u[e]); ct[33 + 8 * i + 2 * e] += bf_hi(u[e]); }
          }
        };
        odd_head(7);
        fetch(pv, 4);
        fetch(p1, 5);
        wg_fence();
        tile_mma(IC<32>(), 7, OA + 4, OB);
        wg_commit();
        uint32_t bad = 0;
#pragma unroll
        for (int i = 0; i < 4; i++) { bad |= (pv[i].x ^ tag) | (p1[i].x ^ tag); pv[i].x &= ~1u; p1[i].x &= ~1u; }
        acc4(pv, p1);
        fetch(p1, 3);
        wg_fence();
        tile_mma(IC<32>(), 7, OB, 14);
        wg_commit();
        if (tid == 0) { PROF_EV(9); PROF_CK(46); }
        if (tid == 128) PROF_EV(29);
        fetch(p2, 6);
        if (tid == 0) PROF_EV(24);
        wg_wait<0>();
        fence_regs<32, 32>(ct);
#pragma unroll
        for (int i = 0; i < 4; i++) bad |= p2[i].x ^ tag;
        if (__any_sync(0xffffffffu, bad & 1)) {
          const uint4* src = ws->part + (size_t)(rb * 8 + j) * 3 * 1024 + fo;
          uint4 p0[4];
          int n = 0;
          do {
            bad = 0;
#pragma unroll
            for (int i = 0; i < 4; i++) {
              pv[i] = ld_x4(src + i * 32); p0[i] = ld_x4(src + 1024 + i * 32); p2[i] = ld_x4(src + 2048 + i * 32);
              bad |= (pv[i].x ^ tag) | (p0[i].x ^ tag) | (p2[i].x ^ tag);
            }
            if (++n > (1 << 21)) __trap();
          } while (__any_sync(0xffffffffu, bad & 1));
#pragma unroll
          for (int i = 0; i < 4; i++) { pv[i].x &= ~1u; p0[i].x &= ~1u; }
          acc4(pv, p0);
        }
#pragma unroll
        for (int i = 0; i < 4; i++) p2[i].x &= ~1u;
        acc4(p1, p2);
        add32(pv); add32(p1);
#pragma unroll
        for (int i = 0; i < 4; i++)
          pv[i] = make_uint4(pack_bf16(ct[32 + 8 * i], ct[33 + 8 * i]), pack_bf16(ct[34 + 8 * i], ct[35 + 8 * i]), pack_bf16(ct[36 + 8 * i], ct[37 + 8 * i]), pack_bf16(ct[38 + 8 * i], ct[39 + 8 * i]));
        if (tid == 0) PROF_EV(14);
        const uint32_t stg = sb + OFF_T + warp * 2048;
        const int mr = (lane & 7) + ((lane >> 3) & 1) * 8, mc = lane >> 4;
#pragma unroll
        for (int i = 0; i < 4; i++)
          asm volatile("stmatrix.sync.aligned.m8n8.x4.shared.b16 [%0], {%1,%2,%3,%4};" ::"r"(stg + mr * 128 + (((2 * i + mc) ^ (mr & 7)) << 4)), "r"(pv[i].x),
                       "r"(pv[i].y), "r"(pv[i].z), "r"(pv[i].w) : "memory");
        __syncwarp();
#pragma unroll
        for (int i = 0; i < 4; i++) {
          const int r = 4 * i + (lane >> 3), c = lane & 7;
          const uint4 v = *(const uint4*)(smem + OFF_T + warp * 2048 + r * 128 + ((c ^ (r & 7)) << 4));
          *(uint4*)(out + (size_t)srow(rb, 16 * warp + r) * 512 + 64 * (q4 + 4 * rank) + 8 * c) = v;
        }
      }
      if (tid == 0) { PROF_EV(15); PROF_CK(41); }
      if (tid == 128) PROF_EV(30);
    }
  } else if (warp < 12) {
    asm volatile("setmaxnreg.dec.sync.aligned.u32 104;");
    asm volatile("barrier.cluster.arrive.relaxed.aligned;" ::: "memory");
    const int t = tid - 256, w = warp - 8;
    const uint32_t ep = ld_x1(&ws->epoch[blockIdx.x * 8]);
    const uint32_t tag = (ep + 1) & 1;
    auto w_issue = [&](const CUtensorMap* m) {

      if (elect_one()) { mbar_expect_tx(bars + 8 * (B_WR + w), 3072); tma4d(sb + OFF_T + w * 3072, m, bars + 8 * (B_WR + w), 32 * j, 0, 2 * w + (rb >> 3), rb & 7); }

          __syncwarp();
    };
    auto gate_rows = [&] {
      const int r = 16 * j + 4 * w + (lane >> 3);
      const uint4* pg = (const uint4*)gate_w + (lane & 7);
      {
        float a = 0.f;
        asm volatile("bar.sync 4, 256;" ::: "memory");
#pragma unroll 1
        for (int hf = 0; hf < 2; hf++) {
          uint4 v[4], u[4];
#pragma unroll
          for (int kb = 0; kb < 4; kb++) v[kb] = __ldg(pg + (4 * hf + kb) * 8);
          mbar_wait(bars + 8 * (B_FE + 1 + 2 * hf), 0);
          if (hf) w_issue(&maps.wr);
#pragma unroll
          for (int kb = 0; kb < 4; kb++) u[kb] = *(const uint4*)(smem + (4 * hf + kb) * U + r * 128 + (((lane ^ r) & 7) << 4));
#pragma unroll
          for (int kb = 0; kb < 4; kb++) {
            const uint32_t uu[4] = {u[kb].x, u[kb].y, u[kb].z, u[kb].w}, vv[4] = {v[kb].x, v[kb].y, v[kb].z, v[kb].w};
#pragma unroll
            for (int e = 0; e < 4; e++) {
              uint32_t pr;
              asm("mul.rn.bf16x2 %0, %1, %2;" : "=r"(pr) : "r"(uu[e]), "r"(vv[e]));
              a += bf_lo(pr) + bf_hi(pr);
            }
          }
        }
#pragma unroll
        for (int o = 4; o; o >>= 1) a += __shfl_xor_sync(0xffffffffu, a, o);
        if ((lane & 7) == 0)
          asm volatile("st.relaxed.gpu.global.u32 [%0], %1;" ::"l"(ws->gate + rb * 128 + r),
                       "r"(pack_bf16(0.f, __fdividef(1.0f, 1.0f + __expf(-bf_lo(pack_bf16(a, 0.f))))) | tag) : "memory");
        if (t == 0) PROF_EV(18);
      }
    };
    {
      const int g = lane >> 2, q = lane & 3;
      uint32_t wf[32];
      if (!helper) {
        gate_rows();
        const uint32_t wa = sb + OFF_T + w * (3072 + 4) + (rb >> 3) * 2 + q * 96 + g * 4, wb[2] = {wa + (rb & 1) * 32, wa + 32 - (rb & 1) * 32};
#pragma unroll 1
        for (int ri = 0; ri < 2; ri++) {
          mbar_wait(bars + 8 * (B_WR + w), ri);
#pragma unroll
          for (int n2 = 0; n2 < 32 / WB; n2++) {
            uint32_t v[WB];
#pragma unroll
            for (int i = 0; i < WB; i++) {
              const int e = n2 * WB + i;
              asm volatile("ld.shared.u16 %0, [%1];" : "=r"(v[i]) : "r"(wb[e & 1] + ((e >> 1) & 7) * 384 + (e >> 4) * 2) : "memory");
            }
#pragma unroll
            for (int i = 0; i < WB; i++) wf[n2 * WB + i] = __byte_perm(wf[n2 * WB + i], v[i], 0x5432);
            if (WSLEEP) { asm volatile("nanosleep.u32 %0;" ::"r"(WSLEEP + (v[WB - 1] >> 16)) : "memory"); }
          }
          __syncwarp();
          if (ri == 0) w_issue(&maps.wi);
        }
        asm volatile("bar.sync 1, 128;" ::: "memory");
        if (t == 0) PROF_EV(11);
      } else {
        asm volatile("bar.sync 4, 256;" ::: "memory");
        hint_wait(&ws->cntW[0], (ep + 1) * 128u);
        const uint32_t t0 = (uint32_t)clock();
#pragma unroll 1
        for (;;) {
          uint32_t bad = 0;
#pragma unroll
          for (int i = 0; i < 32; i++) {
            const float2 v = ld_x2((const float2*)ws->Wh + (i >> 4) * 2048 + 32 * (w & 1) + (w >> 1) + 2 * g + 16 * (i & 1) + 64 * q + ((i >> 1) & 7) * 256);
            wf[i] = __float_as_uint(v.x); bad |= __float_as_uint(v.y) ^ tag;
          }
          if (!__any_sync(0xffffffffu, bad & 1)) break;
          spin_guard(t0);
        }
        if (t == 0) PROF_EV(11);
      }
      if (w == 0 && elect_one()) { mbar_expect_tx(bars + 8 * B_W, 8192); bulk_load(sb + OFF_D, dtab, 8192, bars + 8 * B_W); }
      asm volatile("barrier.cluster.wait.aligned;" ::: "memory");
      mbar_wait(bars + 8 * B_W, 0);
      mbar_wait(bars + 8 * B_HX, 0);
      if (t == 0) PROF_EV(12);
      const uint32_t dd = (sb & 0x3FFFF) >> 4;
      const uint64_t dF = d128((dd + (OFF_D >> 4)) | (512u << 16)), dI = d128((dd + (OFF_D >> 4)) | (1u << 16)), dA = d128((dd + (OFF_XB >> 4)) | (512u << 16));
      float az[32];
      const int zero = blockIdx.x >> 16;
      uint32_t pf[32];
#pragma unroll
      for (int mt = 0; mt < 2; mt++) {
        wg_fence();
        if (mt == 0) mma_ss64<0, 3, 0>(az, dA, dF);
        else mma_ss64<0, 3, 2>(az, dA + 512, dF, zero);
#pragma unroll
        for (int k = 1; k < 4; k++) mma_ss64<0, 3, 1>(az, dA + (mt * 512 + k * 128), dF + k * 128);
        wg_commit();
        wg_wait<0>();
        fence_regs<0, 32>(az);
#pragma unroll
        for (int i = 0; i < 16; i++) {
          const float wr = bf_lo(wf[16 * mt + i]), wi = bf_hi(wf[16 * mt + i]);
          pf[16 * mt + i] = pack_pin(fmaf(az[2 * i], wr, -az[2 * i + 1] * wi), fmaf(az[2 * i], wi, az[2 * i + 1] * wr));
        }
      }
      if (t == 0) PROF_EV(16);
      {
        const int m = lane >> 3, r = lane & 7;
        const int sl = 2 * (m >> 1) + ((r >> 1) & 1) + 4 * (r >> 2);
        const uint32_t a0 = sb + OFF_XB + w * 4096 + sl * 64 + (((((m ^ rb) & 1) * 2 + (r & 1)) ^ (sl >> 1)) << 4);
        uint32_t pk[16];
#pragma unroll
        for (int mt = 0; mt < 3; mt++) {
          if (mt < 2) {
            wg_fence();
            mma_rs64<0, 0, 2>(az, pf[16 * mt], pf[16 * mt + 1], pf[16 * mt + 2], pf[16 * mt + 3], dI, mt ? (int)helper : zero);
#pragma unroll
            for (int k = 1; k < 4; k++) mma_rs64<0, 0, 1>(az, pf[16 * mt + 4 * k], pf[16 * mt + 4 * k + 1], pf[16 * mt + 4 * k + 2], pf[16 * mt + 4 * k + 3], dI + k * 2);
            wg_commit();
          }
          if (mt > 0 && !helper) {
#pragma unroll
            for (int i = 0; i < 4; i++) stsm4t(a0 + (mt - 1) * 2048 + i * 512, pk[4 * i], pk[4 * i + 1], pk[4 * i + 2], pk[4 * i + 3]);
          }
          if (mt < 2) {
            wg_wait<0>();
            fence_regs<0, 32>(az);
#pragma unroll
            for (int i = 0; i < 16; i++) pk[i] = pack_pin(az[2 * i], az[2 * i + 1]);
          }
        }
      }
      if (helper) {
#pragma unroll
        for (int i = 0; i < 16; i++) {
          const int n = i >> 1, s0 = 8 * (n >> 1) + 2 * (n & 1) + (q & 1) + 4 * (q >> 1);
          if ((n & 1) == (int)(blockIdx.x & 1)) st_u2(ws->Ts + s0 * 64 + 16 * w + g + 8 * (i & 1), pack_bf16(az[2 * i], az[2 * i + 1]), tag);
        }
        __syncwarp();
        hint_add_if(lane == 0, &ws->cntH[0]);
        if (t == 0) { ws->epoch[blockIdx.x * 8] = ep + 1; PROF_EV(13); }
      } else {
        asm volatile("fence.proxy.async.shared::cta;" ::: "memory");
        __syncwarp();
        if (elect_one()) {
          if (t == 0) PROF_EV(17);
          if (SPACE) __nanosleep(SPACE * w);
          asm volatile("cp.async.bulk.tensor.4d.global.shared::cta.bulk_group [%0, {%2, %3, %4, %5}], [%1];" ::"l"(&maps.ts), "r"(sb + OFF_XB + w * 4096),
                       "r"(32 * rank), "r"(0), "r"(2 * q4), "r"(4 * rb + w) : "memory");
          bulk_done_signal(&ws->cntT[32 * q4]);
          asm volatile("mbarrier.arrive.shared::cluster.b64 _, [%0];" ::"r"(mapa(bars + 8 * B_RD0, rank ^ 1)) : "memory");
          if (t == 96) PROF_EV(13);
        }
        __syncwarp();
        if (j == 0) {
          hint_wait(&ws->cntH[0], (ep + 1) * 8u);
          const uint32_t t0 = (uint32_t)clock();
          float2 v;
          do { v = ld_x2((const float2*)ws->Ts + 2 * rb * 64 + t); spin_guard(t0); } while (__any_sync(0xffffffffu, (__float_as_uint(v.y) ^ tag) & 1));
          mbar_wait(bars + 8 * B_TL, 0);
          const uint32_t u = __float_as_uint(v.x);
          *(uint16_t*)(smem + OFF_T + t * 128 + ((t & 7) << 4)) = (uint16_t)u;
          *(uint16_t*)(smem + OFF_T + t * 128 + (((t & 7) ^ 1) << 4)) = (uint16_t)(u >> 16);
          asm volatile("fence.proxy.async.shared::cta;" ::: "memory");
          __syncwarp();
          mbar_arrive_if(lane == 0, bars + 8 * B_T);
        }
      }
    }
  } else {
    asm volatile("setmaxnreg.dec.sync.aligned.u32 24;");
    auto xf_load = [&](int q) {
      const uint32_t fb = bars + 8 * (B_FX + q);
      mbar_expect_tx(fb, U + 8192);
      tma5d(sb + q * U, &maps.x, fb, 64 * q, 2 * rb);
      if (q >= 4) mbar_wait(bars + 8 * (B_FE + ((q - 4) >> 1)), 0);
      tma2d(sb + OFF_XB + (q & 3) * 8192, &maps.ft, fb, 64 * q, 64 * j);
    };
    if (elect_one()) {
      if (warp == 14) {
#pragma unroll
        for (int i = 0; i < B_FT; i++) mbar_init(bars + 8 * i, 1);
        asm volatile("fence.mbarrier_init.release.cluster;" ::: "memory");
        if (!helper) {
#pragma unroll 1
          for (int n = 0; n < 2; n++) {
            const uint32_t fb = bars + 8 * (B_FA + n);
            xf_load(2 * n); xf_load(2 * n + 1);
            mbar_expect_tx(fb, U);
            tma2d(sb + OFF_RING + n * U, &maps.g64, fb, f_full, 64 * n);
            tma2d(sb + OFF_RING + n * U + 8192, &maps.u64, fb, f_full, 64 * n);
          }
        }
      } else if (warp == 15) {
#pragma unroll
        for (int i = B_FT; i < NBAR; i++) mbar_init(bars + 8 * i, i < B_EA ? 1 : i < B_T ? 2 : 4);
#pragma unroll
        for (int i = 0; i < 8; i++) mbar_expect_tx(bars + 8 * (B_Z + i), U / 2);
        asm volatile("fence.mbarrier_init.release.cluster;" ::: "memory");
        asm volatile("fence.proxy.async.shared::cta;" ::: "memory");
      }
    }
    __syncwarp();
    asm volatile("bar.arrive 0, 384;" ::: "memory");
    asm volatile("bar.arrive 4, 256;" ::: "memory");
    __syncwarp();
    asm volatile("barrier.cluster.arrive.relaxed.aligned;" ::: "memory");
    asm volatile("bar.sync 3, 128;" ::: "memory");
    if (warp == 15 && !helper) {
        mbar_wait(bars + 8 * B_FE, 0);
        const uint32_t tag = (ld_x1(&ws->epoch[blockIdx.x * 8]) + 1) & 1;
        const int c = lane >> 4, jj = 16 * blockIdx.x + (lane & 15), jm = (2048 - jj) & 2047;
        const unsigned short* pr = (const unsigned short*)w_r + 256 * c;
        const unsigned short* pi = (const unsigned short*)w_i + 256 * c;
        const float wr = 0.25f * (bf_lo(__ldg(pr + jj * 257)) + bf_lo(__ldg(pr + jm * 257)));
        const float wi = 0.25f * (bf_lo(__ldg(pi + jj * 257)) - bf_lo(__ldg(pi + jm * 257)));
        st_u2(ws->Wh + c * 2048 + jj, c ? pack_bf16(-wi, wr) : pack_bf16(wr, wi), tag);
        __syncwarp();
        hint_add_if(lane == 0, &ws->cntW[0]);
        mbar_wait(bars + 8 * B_XS, 0);
        const uint32_t t0 = (uint32_t)clock();
        uint4 v;
        do { v = ld_x4(ws->gate + rb * 128 + 4 * lane); spin_guard(t0); } while (__any_sync(0xffffffffu, ((v.x ^ tag) | (v.y ^ tag) | (v.z ^ tag) | (v.w ^ tag)) & 1));
        *(uint4*)(smem + OFF_G + lane * 16) = v;
        __syncwarp();
        mbar_arrive_if(lane < 4, bars + 8 * B_G);
      }
    auto part_load = [&](int i, unsigned ep1) {
      const uint32_t bytes = i < 2 ? U : U / 2;
      mbar_wait(bars + 8 * (B_PZ + (i == 0)), 0);
      mbar_expect_tx(bars + 8 * (B_HP + i), bytes);
      flag_wait(&ws->cntP[32 * (rb * 8 + j) + 8 * i], ep1 * (i < 2 ? 8u : 4u));
      bulk_load(sb + (i == 0 ? OFF_T : i == 1 ? 0 : i * (U / 2)), ws->part + (size_t)(rb * 8 + j) * 3072 + (i < 2 ? i * 1024 : 1024 + i * 512), bytes, bars + 8 * (B_HP + i));
      if (i == 2) PROF_EV(26);
    };
    if ((!helper || warp == 15) && elect_one()) {
      if (warp < 14) {
        const int p = warp - 12;
#pragma unroll 1
        for (int i = 4 + p; i < 14; i += 2) asm volatile("prefetch.tensormap [%0];" ::"l"((const char*)&maps + i * 128) : "memory");
#pragma unroll 1
        for (int n = 2; n < 30; n++) {
          const bool table = n == 4 || n == 29;
          const bool half = n >= 17 && n < 21;
          const int q = n < 4 ? n : n < 17 ? n - 1 : n - 5;
          const CUtensorMap* m = table ? &maps.e : half ? &maps.g32 + p : &maps.g64 + p;
          const int c0 = table ? 0 : half ? f_half : f_full + 64 * (q >> 3);
          const int c1 = table ? (n & 1) * 2048 + (2 * rb + p) * 64 : half ? 128 * (n - 17) : 64 * (q & 7);
          const uint32_t fb = bars + 8 * (B_FA + (n & 3)), dst = sb + OFF_RING + (n & 3) * U + p * 8192;
          if (n < 4) mbar_wait(bars + 8 * (B_FE + n - 2), 0);
          else mbar_wait(bars + 8 * (B_EA + (n & 3)), ((n >> 2) & 1) ^ 1);
          tma2d(dst, m, fb, c0, c1);
          if (p == 0) mbar_expect_tx(fb, U);
        }
        part_load(2 + p, ld_x1(&ws->epoch[blockIdx.x * 8]) + 1);
      } else if (warp == 15) {
        const unsigned ep1 = ld_x1(&ws->epoch[blockIdx.x * 8]) + 1;
        flag_wait(&ws->cntX[helper ? 0 : 32 * j], ep1 * 16u);
        PROF_EV(22);
        mbar_expect_tx(bars + 8 * B_HX, U);
        bulk_load(sb + OFF_XB, ws->X + (size_t)(helper ? 128 : 16 * j + rb) * 8192, U, bars + 8 * B_HX);
        if (!helper) {
          flag_wait(&ws->cntT[32 * q4], ep1 * 128u);
          PROF_EV(23);
          mbar_expect_tx(bars + 8 * B_TL, U);
          tma3d(sb + OFF_T, &maps.t, bars + 8 * B_TL, 64 * j, 0, 2 * rb);
          part_load(0, ep1); part_load(1, ep1);
          mbar_wait(bars + 8 * (B_HP + 2), 0); mbar_wait(bars + 8 * (B_HP + 3), 0);
          ws->epoch[blockIdx.x * 8] = ep1;
        }
      } else {
#pragma unroll 1
        for (int q = 4; q < 8; q++) xf_load(q);
#pragma unroll 1
        for (int h2 = 0; h2 < 2; h2++) {
          const int s0 = 2 * rb + h2, sg = (s0 & ~6) | ((s0 & 2) << 1) | ((s0 & 4) >> 1);
          mbar_wait(bars + 8 * (B_XS + h2), 0);
#pragma unroll 1
          for (int c = 0; c < 2; c++) {
            asm volatile("cp.async.bulk.tensor.4d.global.shared::cta.bulk_group [%0, {%2, %3, %4, %5}], [%1];" ::"l"(&maps.xs),
                         "r"(sb + OFF_XB + h2 * 8192 + c * 4096), "r"(0), "r"(sg), "r"(0), "r"(16 * j + 8 * c) : "memory");
            if (j == 0)
              asm volatile("cp.async.bulk.global.shared::cta.bulk_group [%0], [%1], 256;" ::"l"(ws->X + 128 * 8192 + c * 4096 + sg * 128),
                           "r"(sb + OFF_SP + h2 * 512 + c * 256) : "memory");
            if (SPACE && h2 + c < 2) __nanosleep(SPACE);
          }
        }
        bulk_done_signal(&ws->cntX[32 * j]);
        PROF_EV(20);
#pragma unroll 1
        for (int t = 0; t < 8; t++) {
          const int col = 64 * (((q4 + 1 + (t >> 1)) & 3) + 4 * ((t & 1) ? rank : 1 - rank));
          const uint32_t fb = bars + 8 * (B_FT + (t & 3)), dst = sb + (t & 3) * TB;
          mbar_wait(bars + 8 * (B_ET + (t < 3 ? t + 1 : t & 3)), t >> 2);
          mbar_expect_tx(fb, (t & 1) ? 28672 : TB);
          tma2d(dst, &maps.d224, fb, col, 224 * j);
          if (!(t & 1)) tma3d(dst + 28672, &maps.fg, fb, col ^ 256, 16 * rank, 4 * q4);
        }
      }
    }
  }
}

typedef CUresult (*EncodeFn)(CUtensorMap*, CUtensorMapDataType, cuuint32_t, void*, const cuuint64_t*, const cuuint64_t*, const cuuint32_t*,
                             const cuuint32_t*, CUtensorMapInterleave, CUtensorMapSwizzle, CUtensorMapL2promotion, CUtensorMapFloatOOBfill);

static void encode(EncodeFn f, CUtensorMap* m, const void* base, int rank, const cuuint64_t* dims, const cuuint64_t* strides, const cuuint32_t* box,
                   CUtensorMapSwizzle sw) {
  cuuint32_t es[5] = {1, 1, 1, 1, 1};
  f(m, CU_TENSOR_MAP_DATA_TYPE_BFLOAT16, rank, (void*)base, dims, strides, box, es, CU_TENSOR_MAP_INTERLEAVE_NONE, sw,
    (CUtensorMapL2promotion)PROMO, CU_TENSOR_MAP_FLOAT_OOB_FILL_NONE);
}

extern "C" void kernel_launch(void* const* d_in, const int* in_sizes, int n_in, void* d_out, int out_size) {
  (void)in_sizes; (void)n_in; (void)out_size;
  const __nv_bfloat16* x = (const __nv_bfloat16*)d_in[0];
  const __nv_bfloat16* w_r = (const __nv_bfloat16*)d_in[1];
  const __nv_bfloat16* w_i = (const __nv_bfloat16*)d_in[2];
  const __nv_bfloat16* Wg = (const __nv_bfloat16*)d_in[4];
  const __nv_bfloat16* Wu = (const __nv_bfloat16*)d_in[5];
  const __nv_bfloat16* Wd = (const __nv_bfloat16*)d_in[6];
  const __nv_bfloat16* gw = (const __nv_bfloat16*)d_in[7];

  void* fp = nullptr; cudaDriverEntryPointQueryResult qr;
  cudaGetDriverEntryPoint("cuTensorMapEncodeTiled", &fp, cudaEnableDefault, &qr);
  EncodeFn enc = (EncodeFn)fp;
  void *pFT, *pET, *pDT, *pW;
  cudaGetSymbolAddress(&pDT, g_DT); cudaGetSymbolAddress(&pW, g_work);
  void *pX = ((Work*)pW)->X, *pT = ((Work*)pW)->T;
  cudaGetSymbolAddress(&pFT, g_FT); cudaGetSymbolAddress(&pET, g_ET);

  Maps mp;
  const CUtensorMapSwizzle S128 = CU_TENSOR_MAP_SWIZZLE_128B, S64 = CU_TENSOR_MAP_SWIZZLE_64B;
  { cuuint64_t d[5] = {512, 8, 2, 4, 32}, s[4] = {32768, 1048576, 262144, 1024}; cuuint32_t b[5] = {64, 8, 2, 4, 2}; encode(enc, &mp.x, x, 5, d, s, b, S128); }
  { cuuint64_t d[2] = {512, 512}, s[1] = {1024}; cuuint32_t b[2] = {64, 64}; encode(enc, &mp.ft, pFT, 2, d, s, b, S128); }
  { cuuint64_t d[4] = {128, 32, 2, 129}, s[3] = {256, 8192, 16384}; cuuint32_t b[4] = {128, 1, 2, 8}; encode(enc, &mp.xs, pX, 4, d, s, b, CU_TENSOR_MAP_SWIZZLE_NONE); }
  { cuuint64_t d[4] = {64, 32, 8, 64}, s[3] = {65536, 128, 1024}; cuuint32_t b[4] = {32, 32, 2, 1}; encode(enc, &mp.ts, pT, 4, d, s, b, S64); }
  { cuuint64_t d[3] = {512, 32, 16}, s[2] = {1024, 32768}; cuuint32_t b[3] = {64, 16, 4}; encode(enc, &mp.fg, pFT, 3, d, s, b, S128); }
  { cuuint64_t d[3] = {512, 64, 32}, s[2] = {1024, 65536}; cuuint32_t b[3] = {64, 64, 2}; encode(enc, &mp.t, pT, 3, d, s, b, S128); }
  { cuuint64_t d[2] = {64, 4096}, s[1] = {128}; cuuint32_t b[2] = {64, 64}; encode(enc, &mp.e, pET, 2, d, s, b, S128); }
  { cuuint64_t d[2] = {1792, 512}, s[1] = {3584}; cuuint32_t b[2] = {64, 64}, b2[2] = {32, 128};
    encode(enc, &mp.g64, Wg, 2, d, s, b, S128); encode(enc, &mp.u64, Wu, 2, d, s, b, S128);
    encode(enc, &mp.g32, Wg, 2, d, s, b2, S64); encode(enc, &mp.u32, Wu, 2, d, s, b2, S64); }
  { cuuint64_t d[2] = {512, 1792}, s[1] = {1024}; cuuint32_t b[2] = {64, 224}; encode(enc, &mp.d224, Wd, 2, d, s, b, S128); }
  { cuuint64_t d[4] = {264, 32, 8, 8}, s[3] = {32896, 512, 4112}; cuuint32_t b[4] = {48, 32, 1, 1};
    encode(enc, &mp.wr, w_r, 4, d, s, b, CU_TENSOR_MAP_SWIZZLE_NONE); encode(enc, &mp.wi, w_i, 4, d, s, b, CU_TENSOR_MAP_SWIZZLE_NONE); }

  cudaFuncSetAttribute(fused_kernel, cudaFuncAttributeMaxDynamicSharedMemorySize, SMEM_BYTES);
  fused_kernel<<<NCTA, 512, SMEM_BYTES>>>((Work*)pW, (const uint16_t*)pDT, w_r, w_i, gw, x, (__nv_bfloat16*)d_out, mp);
}
```

```cpp
#include <cuda_runtime.h>
#include <cuda_bf16.h>
#include <cuda.h>
#include <stdint.h>

namespace tbl {
constexpr double PI = 3.14159265358979323846264338327950288;
constexpr double sin_s(double x) { double t = x, s = x; for (int n = 1; n < 12; n++) { t *= -x * x / ((2 * n) * (2 * n + 1)); s += t; } return s; }
constexpr double cos_s(double x) { double t = 1, s = 1; for (int n = 1; n < 12; n++) { t *= -x * x / ((2 * n - 1) * (2 * n)); s += t; } return s; }
constexpr double cos2048(int m) {
  m &= 2047; if (m > 1024) m = 2048 - m;
  bool neg = false; if (m > 512) { m = 1024 - m; neg = true; }
  double v = (m <= 256) ? cos_s(2 * PI * m / 2048) : sin_s(2 * PI * (512 - m) / 2048);
  return neg ? -v : v;
}
constexpr uint16_t to_bf16(double v) {
  if (v == 0) return 0;
  uint16_t s = 0; if (v < 0) { s = 0x8000; v = -v; }
  int e = 0; while (v >= 2) { v /= 2; e++; } while (v < 1) { v *= 2; e--; }
  double m = (v - 1) * 128; int mi = (int)m; double fr = m - mi;
  if (fr > 0.5 || (fr == 0.5 && (mi & 1))) mi++;
  if (mi == 128) { mi = 0; e++; }
  return (uint16_t)(s | ((e + 127) << 7) | mi);
}
struct CosT { uint16_t v[2048]; constexpr CosT() : v() { for (int i = 0; i < 2048; i++) v[i] = to_bf16(cos2048(i)); } };
struct alignas(1024) FT {
  uint16_t v[512 * 512];
  constexpr FT() : v() {
    CosT c;
    for (int r = 0; r < 512; r++) {
      int k = (r >> 5) * 16 + 2 * (r & 7) + ((r >> 4) & 1), e = (r >> 3) & 1;
      int mul = 4 * k, add = e ? 512 : 0;
      if (k == 0 && e == 1) { mul = 1024; add = 0; }
      for (int d = 0; d < 512; d++) v[r * 512 + d] = c.v[(d * mul + add) & 2047];
    }
  }
};
struct alignas(1024) ET {
  uint16_t v[2 * 32 * 4096];
  constexpr ET() : v() {
    CosT c;
    for (int s = 0; s < 1024; s++)
      for (int j1 = 0; j1 < 64; j1++)
        for (int e = 0; e < 2; e++) {
          const int s0 = s & 31, i = s >> 5, p = j1 & 1, j = j1 >> 1;
          const uint16_t x = c.v[(s * j1 + 512 * e) & 2047];
          v[s0 * 4096 + (p * 32 + i) * 64 + e * 32 + j] = x;
          v[(32 + s0) * 4096 + ((i >> 3) * 16 + e * 8 + (i & 7)) * 64 + p * 32 + j] = x;
        }
  }
};
struct alignas(1024) DT {
  uint16_t v[64 * 64];
  constexpr DT() : v() {
    CosT c;
    for (int r = 0; r < 64; r++)
      for (int n = 0; n < 64; n++) {
        const int sg = r >> 1, s0 = (sg & ~6) | ((sg & 2) << 1) | ((sg & 4) >> 1), e = r & 1, f = n & 1;
        const int m = 64 * s0 * (n >> 1) + (e == f ? 0 : e ? -512 : 512);
        v[r * 64 + (((n >> 3) ^ (r & 7)) << 3) + (n & 7)] = c.v[m & 2047];
      }
  }
};
}

__device__ constexpr tbl::FT g_FT = tbl::FT();
__device__ constexpr tbl::ET g_ET = tbl::ET();
__device__ constexpr tbl::DT g_DT = tbl::DT();

struct alignas(1024) Work {
  unsigned epoch[132 * 8];
  unsigned cntX[8 * 32], cntT[8 * 32], cntP[128 * 32], cntW[32], cntH[32];
  alignas(16) float gate[16 * 128];
  alignas(16) uint2 Wh[2 * 2048];
  alignas(16) uint2 Ts[32 * 64];
  alignas(1024) uint16_t X[129 * 8192];
  alignas(1024) uint16_t T[32 * 64 * 512];
  alignas(1024) uint4 part[128 * 3 * 1024];
};
__device__ Work g_work;
#define PROF_EV(i) do {} while (0)
#define PROF_CK(i) do {} while (0)

__device__ __forceinline__ uint32_t smem_u32(const void* p) { return (uint32_t)__cvta_generic_to_shared(p); }
__device__ __forceinline__ void mbar_init(uint32_t bar, uint32_t cnt) { asm volatile("mbarrier.init.shared::cta.b64 [%0], %1;" ::"r"(bar), "r"(cnt)); }
__device__ __forceinline__ void mbar_expect_tx(uint32_t bar, uint32_t bytes) { asm volatile("mbarrier.arrive.expect_tx.shared::cta.b64 _, [%0], %1;" ::"r"(bar), "r"(bytes) : "memory"); }
__device__ __forceinline__ void mbar_arrive(uint32_t bar) { asm volatile("mbarrier.arrive.shared::cta.b64 _, [%0];" ::"r"(bar) : "memory"); }
__device__ __forceinline__ bool elect_one() {
  uint32_t p;
  asm volatile("{\n.reg .pred p;\nelect.sync _|p, 0xffffffff;\nselp.u32 %0, 1, 0, p;\n}" : "=r"(p));
  return p;
}
__device__ __forceinline__ void mbar_arrive_if(bool p, uint32_t bar) {
  asm volatile("{\n.reg .pred p;\nsetp.ne.b32 p, %1, 0;\n@p mbarrier.arrive.shared::cta.b64 _, [%0];\n}" ::"r"(bar), "r"((int)p) : "memory");
}
__device__ __forceinline__ void hint_add_if(bool p, unsigned* a) {
  asm volatile("{\n.reg .pred p;\nsetp.ne.b32 p, %1, 0;\n@p red.relaxed.gpu.global.add.u32 [%0], 1;\n}" ::"l"(a), "r"((int)p) : "memory");
}
__device__ __forceinline__ bool mbar_try(uint32_t bar, uint32_t parity) {
  uint32_t ok;
  asm volatile("{\n.reg .pred p;\nmbarrier.test_wait.parity.shared::cta.b64 p, [%1], %2;\nselp.u32 %0, 1, 0, p;\n}" : "=r"(ok) : "r"(bar), "r"(parity) : "memory");
  return ok;
}
__device__ __forceinline__ void mbar_wait(uint32_t bar, uint32_t parity) {
  asm volatile(
      "{\n.reg .pred p;\n.reg .u32 n;\nmov.u32 n, 0;\n"
      "W_LOOP:\nmbarrier.try_wait.parity.shared::cta.b64 p, [%0], %1;\n@p bra W_DONE;\n"
      "add.u32 n, n, 1;\nsetp.lt.u32 p, n, 0x40000;\n@p bra W_LOOP;\ntrap;\nW_DONE:\n}" ::"r"(bar), "r"(parity) : "memory");
}
__device__ __forceinline__ void bulk_load(uint32_t dst, const void* src, uint32_t bytes, uint32_t bar) {
  asm volatile("cp.async.bulk.shared::cluster.global.mbarrier::complete_tx::bytes [%0], [%1], %2, [%3];" ::"r"(dst), "l"(src), "r"(bytes), "r"(bar) : "memory");
}
__device__ __forceinline__ void spin_guard(uint32_t t0) { if ((uint32_t)clock() - t0 > (1u << 30)) __trap(); }
__device__ __forceinline__ float2 ld_x2(const float2* p) { float2 v; asm volatile("ld.relaxed.gpu.global.v2.f32 {%0,%1}, [%2];" : "=f"(v.x), "=f"(v.y) : "l"(p) : "memory"); return v; }
__device__ __forceinline__ void st_u2(uint2* p, uint32_t a, uint32_t b) { asm volatile("st.relaxed.gpu.global.v2.u32 [%0], {%1,%2};" ::"l"(p), "r"(a), "r"(b) : "memory"); }
__device__ __forceinline__ uint32_t ld_x1(const void* p) { uint32_t v; asm volatile("ld.relaxed.gpu.global.u32 %0, [%1];" : "=r"(v) : "l"(p) : "memory"); return v; }
__device__ __forceinline__ uint4 ld_x4(const void* p) { uint4 v; asm volatile("ld.relaxed.gpu.global.v4.u32 {%0,%1,%2,%3}, [%4];" : "=r"(v.x), "=r"(v.y), "=r"(v.z), "=r"(v.w) : "l"(p) : "memory"); return v; }
__device__ __forceinline__ uint32_t mapa(uint32_t a, uint32_t cta) { uint32_t r; asm volatile("mapa.shared::cluster.u32 %0, %1, %2;" : "=r"(r) : "r"(a), "r"(cta)); return r; }
__device__ __forceinline__ void stsm4t(uint32_t a, uint32_t r0, uint32_t r1, uint32_t r2, uint32_t r3) {
  asm volatile("stmatrix.sync.aligned.m8n8.x4.trans.shared.b16 [%0], {%1,%2,%3,%4};" ::"r"(a), "r"(r0), "r"(r1), "r"(r2), "r"(r3) : "memory");
}
__device__ __forceinline__ void hint_add(unsigned* p) { asm volatile("red.relaxed.gpu.global.add.u32 [%0], 1;" ::"l"(p) : "memory"); }
__device__ __forceinline__ void hint_wait(const unsigned* p, unsigned target) {
  const uint32_t t0 = (uint32_t)clock();
  while ((int)(ld_x1(p) - target) < 0) spin_guard(t0);
}
__device__ __forceinline__ void bulk_done_signal(unsigned* p) {
  asm volatile("cp.async.bulk.commit_group;\ncp.async.bulk.wait_group 0;\nfence.proxy.async.global;" ::: "memory");
  hint_add(p);
}
__device__ __forceinline__ void flag_wait(const unsigned* p, unsigned target) {
  hint_wait(p, target);
  asm volatile("fence.proxy.async.global;" ::: "memory");
}
__device__ __forceinline__ void tma2d(uint32_t dst, const CUtensorMap* m, uint32_t bar, int c0, int c1) {
  asm volatile("cp.async.bulk.tensor.2d.shared::cluster.global.mbarrier::complete_tx::bytes [%0], [%1, {%3, %4}], [%2];" ::"r"(dst), "l"(m), "r"(bar), "r"(c0), "r"(c1) : "memory");
}
__device__ __forceinline__ void tma3d(uint32_t dst, const CUtensorMap* m, uint32_t bar, int c0, int c1, int c2) {
  asm volatile("cp.async.bulk.tensor.3d.shared::cluster.global.mbarrier::complete_tx::bytes [%0], [%1, {%3, %4, %5}], [%2];" ::"r"(dst), "l"(m), "r"(bar), "r"(c0), "r"(c1), "r"(c2) : "memory");
}
__device__ __forceinline__ void tma4d(uint32_t dst, const CUtensorMap* m, uint32_t bar, int c0, int c1, int c2, int c3) {
  asm volatile("cp.async.bulk.tensor.4d.shared::cluster.global.mbarrier::complete_tx::bytes [%0], [%1, {%3, %4, %5, %6}], [%2];" ::"r"(dst), "l"(m), "r"(bar), "r"(c0), "r"(c1), "r"(c2), "r"(c3) : "memory");
}
__device__ __forceinline__ void tma5d(uint32_t dst, const CUtensorMap* m, uint32_t bar, int c0, int c4) {
  asm volatile("cp.async.bulk.tensor.5d.shared::cluster.global.mbarrier::complete_tx::bytes [%0], [%1, {%3, %5, %5, %5, %4}], [%2];" ::"r"(dst), "l"(m), "r"(bar), "r"(c0), "r"(c4), "r"(0) : "memory");
}
__device__ __forceinline__ void wg_fence() { asm volatile("wgmma.fence.sync.aligned;" ::: "memory"); }
__device__ __forceinline__ void wg_commit() { asm volatile("wgmma.commit_group.sync.aligned;" ::: "memory"); }
template <int N> __device__ __forceinline__ void wg_wait() { asm volatile("wgmma.wait_group.sync.aligned %0;" ::"n"(N) : "memory"); }
template <int O, int N, int NN> __device__ __forceinline__ void fence_regs(float (&d)[NN]) {
#pragma unroll
  for (int i = 0; i < N; i++) asm volatile("" : "+f"(d[O + i])::"memory");
}
__device__ __forceinline__ uint32_t pack_bf16(float lo, float hi) {
  uint32_t r; asm("cvt.rn.bf16x2.f32 %0, %1, %2;" : "=r"(r) : "f"(hi), "f"(lo)); return r;
}
__device__ __forceinline__ uint32_t pack_pin(float lo, float hi) {
  uint32_t r; asm volatile("cvt.rn.bf16x2.f32 %0, %1, %2;" : "=r"(r) : "f"(hi), "f"(lo) : "memory"); return r;
}
__device__ __forceinline__ uint32_t add_bf2(uint32_t a, uint32_t b) { uint32_t r; asm("add.rn.bf16x2 %0, %1, %2;" : "=r"(r) : "r"(a), "r"(b)); return r; }
__device__ __forceinline__ float bf_lo(uint32_t u) { return __uint_as_float(u << 16); }
__device__ __forceinline__ float bf_hi(uint32_t u) { return __uint_as_float(u & 0xffff0000u); }

__device__ __forceinline__ uint64_t d128(uint32_t lo) { uint64_t d; asm("mov.b64 %0, {%1, 0x40000040};" : "=l"(d) : "r"(lo)); return d; }
__device__ __forceinline__ uint64_t d64(uint32_t lo) { uint64_t d; asm("mov.b64 %0, {%1, 0x80000020};" : "=l"(d) : "r"(lo)); return d; }
template<int O,int TB,int ACC,int NN> __device__ __forceinline__ void mma_ss64(float (&d)[NN], uint64_t da, uint64_t db, int sd = 0){
  if constexpr (ACC == 1) asm volatile("wgmma.mma_async.sync.aligned.m64n64k16.f32.bf16.bf16 {%0,%1,%2,%3,%4,%5,%6,%7,%8,%9,%10,%11,%12,%13,%14,%15,%16,%17,%18,%19,%20,%21,%22,%23,%24,%25,%26,%27,%28,%29,%30,%31}, %32, %33, 1, 1, 1, %35, %34;"
   : "+f"(d[O+0]), "+f"(d[O+1]), "+f"(d[O+2]), "+f"(d[O+3]), "+f"(d[O+4]), "+f"(d[O+5]), "+f"(d[O+6]), "+f"(d[O+7]), "+f"(d[O+8]), "+f"(d[O+9]), "+f"(d[O+10]), "+f"(d[O+11]), "+f"(d[O+12]), "+f"(d[O+13]), "+f"(d[O+14]), "+f"(d[O+15]), "+f"(d[O+16]), "+f"(d[O+17]), "+f"(d[O+18]), "+f"(d[O+19]), "+f"(d[O+20]), "+f"(d[O+21]), "+f"(d[O+22]), "+f"(d[O+23]), "+f"(d[O+24]), "+f"(d[O+25]), "+f"(d[O+26]), "+f"(d[O+27]), "+f"(d[O+28]), "+f"(d[O+29]), "+f"(d[O+30]), "+f"(d[O+31])
   : "l"(da), "l"(db), "n"(TB & 1), "n"(TB >> 1));
  else if constexpr (ACC == 0) asm volatile("wgmma.mma_async.sync.aligned.m64n64k16.f32.bf16.bf16 {%0,%1,%2,%3,%4,%5,%6,%7,%8,%9,%10,%11,%12,%13,%14,%15,%16,%17,%18,%19,%20,%21,%22,%23,%24,%25,%26,%27,%28,%29,%30,%31}, %32, %33, 0, 1, 1, %35, %34;"
   : "=f"(d[O+0]), "=f"(d[O+1]), "=f"(d[O+2]), "=f"(d[O+3]), "=f"(d[O+4]), "=f"(d[O+5]), "=f"(d[O+6]), "=f"(d[O+7]), "=f"(d[O+8]), "=f"(d[O+9]), "=f"(d[O+10]), "=f"(d[O+11]), "=f"(d[O+12]), "=f"(d[O+13]), "=f"(d[O+14]), "=f"(d[O+15]), "=f"(d[O+16]), "=f"(d[O+17]), "=f"(d[O+18]), "=f"(d[O+19]), "=f"(d[O+20]), "=f"(d[O+21]), "=f"(d[O+22]), "=f"(d[O+23]), "=f"(d[O+24]), "=f"(d[O+25]), "=f"(d[O+26]), "=f"(d[O+27]), "=f"(d[O+28]), "=f"(d[O+29]), "=f"(d[O+30]), "=f"(d[O+31])
   : "l"(da), "l"(db), "n"(TB & 1), "n"(TB >> 1));
  else asm volatile("{\n.reg .pred p;\nsetp.ne.b32 p, %36, 0;\nwgmma.mma_async.sync.aligned.m64n64k16.f32.bf16.bf16 {%0,%1,%2,%3,%4,%5,%6,%7,%8,%9,%10,%11,%12,%13,%14,%15,%16,%17,%18,%19,%20,%21,%22,%23,%24,%25,%26,%27,%28,%29,%30,%31}, %32, %33, p, 1, 1, %35, %34;\n}"
   : "+f"(d[O+0]), "+f"(d[O+1]), "+f"(d[O+2]), "+f"(d[O+3]), "+f"(d[O+4]), "+f"(d[O+5]), "+f"(d[O+6]), "+f"(d[O+7]), "+f"(d[O+8]), "+f"(d[O+9]), "+f"(d[O+10]), "+f"(d[O+11]), "+f"(d[O+12]), "+f"(d[O+13]), "+f"(d[O+14]), "+f"(d[O+15]), "+f"(d[O+16]), "+f"(d[O+17]), "+f"(d[O+18]), "+f"(d[O+19]), "+f"(d[O+20]), "+f"(d[O+21]), "+f"(d[O+22]), "+f"(d[O+23]), "+f"(d[O+24]), "+f"(d[O+25]), "+f"(d[O+26]), "+f"(d[O+27]), "+f"(d[O+28]), "+f"(d[O+29]), "+f"(d[O+30]), "+f"(d[O+31])
   : "l"(da), "l"(db), "n"(TB & 1), "n"(TB >> 1), "r"(sd));
}
template<int O,int TB,int ACC,int NN> __device__ __forceinline__ void mma_rs64(float (&d)[NN], uint32_t a0, uint32_t a1, uint32_t a2, uint32_t a3, uint64_t db, int sd = 0){
  if constexpr (ACC == 1) asm volatile("wgmma.mma_async.sync.aligned.m64n64k16.f32.bf16.bf16 {%0,%1,%2,%3,%4,%5,%6,%7,%8,%9,%10,%11,%12,%13,%14,%15,%16,%17,%18,%19,%20,%21,%22,%23,%24,%25,%26,%27,%28,%29,%30,%31}, {%32,%33,%34,%35}, %36, 1, 1, 1, %37;"
   : "+f"(d[O+0]), "+f"(d[O+1]), "+f"(d[O+2]), "+f"(d[O+3]), "+f"(d[O+4]), "+f"(d[O+5]), "+f"(d[O+6]), "+f"(d[O+7]), "+f"(d[O+8]), "+f"(d[O+9]), "+f"(d[O+10]), "+f"(d[O+11]), "+f"(d[O+12]), "+f"(d[O+13]), "+f"(d[O+14]), "+f"(d[O+15]), "+f"(d[O+16]), "+f"(d[O+17]), "+f"(d[O+18]), "+f"(d[O+19]), "+f"(d[O+20]), "+f"(d[O+21]), "+f"(d[O+22]), "+f"(d[O+23]), "+f"(d[O+24]), "+f"(d[O+25]), "+f"(d[O+26]), "+f"(d[O+27]), "+f"(d[O+28]), "+f"(d[O+29]), "+f"(d[O+30]), "+f"(d[O+31])
   : "r"(a0), "r"(a1), "r"(a2), "r"(a3), "l"(db), "n"(TB));
  else if constexpr (ACC == 0) asm volatile("wgmma.mma_async.sync.aligned.m64n64k16.f32.bf16.bf16 {%0,%1,%2,%3,%4,%5,%6,%7,%8,%9,%10,%11,%12,%13,%14,%15,%16,%17,%18,%19,%20,%21,%22,%23,%24,%25,%26,%27,%28,%29,%30,%31}, {%32,%33,%34,%35}, %36, 0, 1, 1, %37;"
   : "=f"(d[O+0]), "=f"(d[O+1]), "=f"(d[O+2]), "=f"(d[O+3]), "=f"(d[O+4]), "=f"(d[O+5]), "=f"(d[O+6]), "=f"(d[O+7]), "=f"(d[O+8]), "=f"(d[O+9]), "=f"(d[O+10]), "=f"(d[O+11]), "=f"(d[O+12]), "=f"(d[O+13]), "=f"(d[O+14]), "=f"(d[O+15]), "=f"(d[O+16]), "=f"(d[O+17]), "=f"(d[O+18]), "=f"(d[O+19]), "=f"(d[O+20]), "=f"(d[O+21]), "=f"(d[O+22]), "=f"(d[O+23]), "=f"(d[O+24]), "=f"(d[O+25]), "=f"(d[O+26]), "=f"(d[O+27]), "=f"(d[O+28]), "=f"(d[O+29]), "=f"(d[O+30]), "=f"(d[O+31])
   : "r"(a0), "r"(a1), "r"(a2), "r"(a3), "l"(db), "n"(TB));
  else asm volatile("{\n.reg .pred p;\nsetp.ne.b32 p, %38, 0;\nwgmma.mma_async.sync.aligned.m64n64k16.f32.bf16.bf16 {%0,%1,%2,%3,%4,%5,%6,%7,%8,%9,%10,%11,%12,%13,%14,%15,%16,%17,%18,%19,%20,%21,%22,%23,%24,%25,%26,%27,%28,%29,%30,%31}, {%32,%33,%34,%35}, %36, p, 1, 1, %37;\n}"
   : "+f"(d[O+0]), "+f"(d[O+1]), "+f"(d[O+2]), "+f"(d[O+3]), "+f"(d[O+4]), "+f"(d[O+5]), "+f"(d[O+6]), "+f"(d[O+7]), "+f"(d[O+8]), "+f"(d[O+9]), "+f"(d[O+10]), "+f"(d[O+11]), "+f"(d[O+12]), "+f"(d[O+13]), "+f"(d[O+14]), "+f"(d[O+15]), "+f"(d[O+16]), "+f"(d[O+17]), "+f"(d[O+18]), "+f"(d[O+19]), "+f"(d[O+20]), "+f"(d[O+21]), "+f"(d[O+22]), "+f"(d[O+23]), "+f"(d[O+24]), "+f"(d[O+25]), "+f"(d[O+26]), "+f"(d[O+27]), "+f"(d[O+28]), "+f"(d[O+29]), "+f"(d[O+30]), "+f"(d[O+31])
   : "r"(a0), "r"(a1), "r"(a2), "r"(a3), "l"(db), "n"(TB), "r"(sd));
}
template<int O,int TB,int ACC,int NN> __device__ __forceinline__ void mma_ss128(float (&d)[NN], uint64_t da, uint64_t db, int sd = 0){
  if constexpr (ACC == 1) asm volatile("wgmma.mma_async.sync.aligned.m64n128k16.f32.bf16.bf16 {%0,%1,%2,%3,%4,%5,%6,%7,%8,%9,%10,%11,%12,%13,%14,%15,%16,%17,%18,%19,%20,%21,%22,%23,%24,%25,%26,%27,%28,%29,%30,%31,%32,%33,%34,%35,%36,%37,%38,%39,%40,%41,%42,%43,%44,%45,%46,%47,%48,%49,%50,%51,%52,%53,%54,%55,%56,%57,%58,%59,%60,%61,%62,%63}, %64, %65, 1, 1, 1, %67, %66;"
   : "+f"(d[O+0]), "+f"(d[O+1]), "+f"(d[O+2]), "+f"(d[O+3]), "+f"(d[O+4]), "+f"(d[O+5]), "+f"(d[O+6]), "+f"(d[O+7]), "+f"(d[O+8]), "+f"(d[O+9]), "+f"(d[O+10]), "+f"(d[O+11]), "+f"(d[O+12]), "+f"(d[O+13]), "+f"(d[O+14]), "+f"(d[O+15]), "+f"(d[O+16]), "+f"(d[O+17]), "+f"(d[O+18]), "+f"(d[O+19]), "+f"(d[O+20]), "+f"(d[O+21]), "+f"(d[O+22]), "+f"(d[O+23]), "+f"(d[O+24]), "+f"(d[O+25]), "+f"(d[O+26]), "+f"(d[O+27]), "+f"(d[O+28]), "+f"(d[O+29]), "+f"(d[O+30]), "+f"(d[O+31]), "+f"(d[O+32]), "+f"(d[O+33]), "+f"(d[O+34]), "+f"(d[O+35]), "+f"(d[O+36]), "+f"(d[O+37]), "+f"(d[O+38]), "+f"(d[O+39]), "+f"(d[O+40]), "+f"(d[O+41]), "+f"(d[O+42]), "+f"(d[O+43]), "+f"(d[O+44]), "+f"(d[O+45]), "+f"(d[O+46]), "+f"(d[O+47]), "+f"(d[O+48]), "+f"(d[O+49]), "+f"(d[O+50]), "+f"(d[O+51]), "+f"(d[O+52]), "+f"(d[O+53]), "+f"(d[O+54]), "+f"(d[O+55]), "+f"(d[O+56]), "+f"(d[O+57]), "+f"(d[O+58]), "+f"(d[O+59]), "+f"(d[O+60]), "+f"(d[O+61]), "+f"(d[O+62]), "+f"(d[O+63])
   : "l"(da), "l"(db), "n"(TB & 1), "n"(TB >> 1));
  else if constexpr (ACC == 0) asm volatile("wgmma.mma_async.sync.aligned.m64n128k16.f32.bf16.bf16 {%0,%1,%2,%3,%4,%5,%6,%7,%8,%9,%10,%11,%12,%13,%14,%15,%16,%17,%18,%19,%20,%21,%22,%23,%24,%25,%26,%27,%28,%29,%30,%31,%32,%33,%34,%35,%36,%37,%38,%39,%40,%41,%42,%43,%44,%45,%46,%47,%48,%49,%50,%51,%52,%53,%54,%55,%56,%57,%58,%59,%60,%61,%62,%63}, %64, %65, 0, 1, 1, %67, %66;"
   : "=f"(d[O+0]), "=f"(d[O+1]), "=f"(d[O+2]), "=f"(d[O+3]), "=f"(d[O+4]), "=f"(d[O+5]), "=f"(d[O+6]), "=f"(d[O+7]), "=f"(d[O+8]), "=f"(d[O+9]), "=f"(d[O+10]), "=f"(d[O+11]), "=f"(d[O+12]), "=f"(d[O+13]), "=f"(d[O+14]), "=f"(d[O+15]), "=f"(d[O+16]), "=f"(d[O+17]), "=f"(d[O+18]), "=f"(d[O+19]), "=f"(d[O+20]), "=f"(d[O+21]), "=f"(d[O+22]), "=f"(d[O+23]), "=f"(d[O+24]), "=f"(d[O+25]), "=f"(d[O+26]), "=f"(d[O+27]), "=f"(d[O+28]), "=f"(d[O+29]), "=f"(d[O+30]), "=f"(d[O+31]), "=f"(d[O+32]), "=f"(d[O+33]), "=f"(d[O+34]), "=f"(d[O+35]), "=f"(d[O+36]), "=f"(d[O+37]), "=f"(d[O+38]), "=f"(d[O+39]), "=f"(d[O+40]), "=f"(d[O+41]), "=f"(d[O+42]), "=f"(d[O+43]), "=f"(d[O+44]), "=f"(d[O+45]), "=f"(d[O+46]), "=f"(d[O+47]), "=f"(d[O+48]), "=f"(d[O+49]), "=f"(d[O+50]), "=f"(d[O+51]), "=f"(d[O+52]), "=f"(d[O+53]), "=f"(d[O+54]), "=f"(d[O+55]), "=f"(d[O+56]), "=f"(d[O+57]), "=f"(d[O+58]), "=f"(d[O+59]), "=f"(d[O+60]), "=f"(d[O+61]), "=f"(d[O+62]), "=f"(d[O+63])
   : "l"(da), "l"(db), "n"(TB & 1), "n"(TB >> 1));
  else asm volatile("{\n.reg .pred p;\nsetp.ne.b32 p, %68, 0;\nwgmma.mma_async.sync.aligned.m64n128k16.f32.bf16.bf16 {%0,%1,%2,%3,%4,%5,%6,%7,%8,%9,%10,%11,%12,%13,%14,%15,%16,%17,%18,%19,%20,%21,%22,%23,%24,%25,%26,%27,%28,%29,%30,%31,%32,%33,%34,%35,%36,%37,%38,%39,%40,%41,%42,%43,%44,%45,%46,%47,%48,%49,%50,%51,%52,%53,%54,%55,%56,%57,%58,%59,%60,%61,%62,%63}, %64, %65, p, 1, 1, %67, %66;\n}"
   : "+f"(d[O+0]), "+f"(d[O+1]), "+f"(d[O+2]), "+f"(d[O+3]), "+f"(d[O+4]), "+f"(d[O+5]), "+f"(d[O+6]), "+f"(d[O+7]), "+f"(d[O+8]), "+f"(d[O+9]), "+f"(d[O+10]), "+f"(d[O+11]), "+f"(d[O+12]), "+f"(d[O+13]), "+f"(d[O+14]), "+f"(d[O+15]), "+f"(d[O+16]), "+f"(d[O+17]), "+f"(d[O+18]), "+f"(d[O+19]), "+f"(d[O+20]), "+f"(d[O+21]), "+f"(d[O+22]), "+f"(d[O+23]), "+f"(d[O+24]), "+f"(d[O+25]), "+f"(d[O+26]), "+f"(d[O+27]), "+f"(d[O+28]), "+f"(d[O+29]), "+f"(d[O+30]), "+f"(d[O+31]), "+f"(d[O+32]), "+f"(d[O+33]), "+f"(d[O+34]), "+f"(d[O+35]), "+f"(d[O+36]), "+f"(d[O+37]), "+f"(d[O+38]), "+f"(d[O+39]), "+f"(d[O+40]), "+f"(d[O+41]), "+f"(d[O+42]), "+f"(d[O+43]), "+f"(d[O+44]), "+f"(d[O+45]), "+f"(d[O+46]), "+f"(d[O+47]), "+f"(d[O+48]), "+f"(d[O+49]), "+f"(d[O+50]), "+f"(d[O+51]), "+f"(d[O+52]), "+f"(d[O+53]), "+f"(d[O+54]), "+f"(d[O+55]), "+f"(d[O+56]), "+f"(d[O+57]), "+f"(d[O+58]), "+f"(d[O+59]), "+f"(d[O+60]), "+f"(d[O+61]), "+f"(d[O+62]), "+f"(d[O+63])
   : "l"(da), "l"(db), "n"(TB & 1), "n"(TB >> 1), "r"(sd));
}
template<int O,int TB,int ACC,int NN> __device__ __forceinline__ void mma_rs128(float (&d)[NN], uint32_t a0, uint32_t a1, uint32_t a2, uint32_t a3, uint64_t db, int sd = 0){
  if constexpr (ACC == 1) asm volatile("wgmma.mma_async.sync.aligned.m64n128k16.f32.bf16.bf16 {%0,%1,%2,%3,%4,%5,%6,%7,%8,%9,%10,%11,%12,%13,%14,%15,%16,%17,%18,%19,%20,%21,%22,%23,%24,%25,%26,%27,%28,%29,%30,%31,%32,%33,%34,%35,%36,%37,%38,%39,%40,%41,%42,%43,%44,%45,%46,%47,%48,%49,%50,%51,%52,%53,%54,%55,%56,%57,%58,%59,%60,%61,%62,%63}, {%64,%65,%66,%67}, %68, 1, 1, 1, %69;"
   : "+f"(d[O+0]), "+f"(d[O+1]), "+f"(d[O+2]), "+f"(d[O+3]), "+f"(d[O+4]), "+f"(d[O+5]), "+f"(d[O+6]), "+f"(d[O+7]), "+f"(d[O+8]), "+f"(d[O+9]), "+f"(d[O+10]), "+f"(d[O+11]), "+f"(d[O+12]), "+f"(d[O+13]), "+f"(d[O+14]), "+f"(d[O+15]), "+f"(d[O+16]), "+f"(d[O+17]), "+f"(d[O+18]), "+f"(d[O+19]), "+f"(d[O+20]), "+f"(d[O+21]), "+f"(d[O+22]), "+f"(d[O+23]), "+f"(d[O+24]), "+f"(d[O+25]), "+f"(d[O+26]), "+f"(d[O+27]), "+f"(d[O+28]), "+f"(d[O+29]), "+f"(d[O+30]), "+f"(d[O+31]), "+f"(d[O+32]), "+f"(d[O+33]), "+f"(d[O+34]), "+f"(d[O+35]), "+f"(d[O+36]), "+f"(d[O+37]), "+f"(d[O+38]), "+f"(d[O+39]), "+f"(d[O+40]), "+f"(d[O+41]), "+f"(d[O+42]), "+f"(d[O+43]), "+f"(d[O+44]), "+f"(d[O+45]), "+f"(d[O+46]), "+f"(d[O+47]), "+f"(d[O+48]), "+f"(d[O+49]), "+f"(d[O+50]), "+f"(d[O+51]), "+f"(d[O+52]), "+f"(d[O+53]), "+f"(d[O+54]), "+f"(d[O+55]), "+f"(d[O+56]), "+f"(d[O+57]), "+f"(d[O+58]), "+f"(d[O+59]), "+f"(d[O+60]), "+f"(d[O+61]), "+f"(d[O+62]), "+f"(d[O+63])
   : "r"(a0), "r"(a1), "r"(a2), "r"(a3), "l"(db), "n"(TB));
  else if constexpr (ACC == 0) asm volatile("wgmma.mma_async.sync.aligned.m64n128k16.f32.bf16.bf16 {%0,%1,%2,%3,%4,%5,%6,%7,%8,%9,%10,%11,%12,%13,%14,%15,%16,%17,%18,%19,%20,%21,%22,%23,%24,%25,%26,%27,%28,%29,%30,%31,%32,%33,%34,%35,%36,%37,%38,%39,%40,%41,%42,%43,%44,%45,%46,%47,%48,%49,%50,%51,%52,%53,%54,%55,%56,%57,%58,%59,%60,%61,%62,%63}, {%64,%65,%66,%67}, %68, 0, 1, 1, %69;"
   : "=f"(d[O+0]), "=f"(d[O+1]), "=f"(d[O+2]), "=f"(d[O+3]), "=f"(d[O+4]), "=f"(d[O+5]), "=f"(d[O+6]), "=f"(d[O+7]), "=f"(d[O+8]), "=f"(d[O+9]), "=f"(d[O+10]), "=f"(d[O+11]), "=f"(d[O+12]), "=f"(d[O+13]), "=f"(d[O+14]), "=f"(d[O+15]), "=f"(d[O+16]), "=f"(d[O+17]), "=f"(d[O+18]), "=f"(d[O+19]), "=f"(d[O+20]), "=f"(d[O+21]), "=f"(d[O+22]), "=f"(d[O+23]), "=f"(d[O+24]), "=f"(d[O+25]), "=f"(d[O+26]), "=f"(d[O+27]), "=f"(d[O+28]), "=f"(d[O+29]), "=f"(d[O+30]), "=f"(d[O+31]), "=f"(d[O+32]), "=f"(d[O+33]), "=f"(d[O+34]), "=f"(d[O+35]), "=f"(d[O+36]), "=f"(d[O+37]), "=f"(d[O+38]), "=f"(d[O+39]), "=f"(d[O+40]), "=f"(d[O+41]), "=f"(d[O+42]), "=f"(d[O+43]), "=f"(d[O+44]), "=f"(d[O+45]), "=f"(d[O+46]), "=f"(d[O+47]), "=f"(d[O+48]), "=f"(d[O+49]), "=f"(d[O+50]), "=f"(d[O+51]), "=f"(d[O+52]), "=f"(d[O+53]), "=f"(d[O+54]), "=f"(d[O+55]), "=f"(d[O+56]), "=f"(d[O+57]), "=f"(d[O+58]), "=f"(d[O+59]), "=f"(d[O+60]), "=f"(d[O+61]), "=f"(d[O+62]), "=f"(d[O+63])
   : "r"(a0), "r"(a1), "r"(a2), "r"(a3), "l"(db), "n"(TB));
  else asm volatile("{\n.reg .pred p;\nsetp.ne.b32 p, %70, 0;\nwgmma.mma_async.sync.aligned.m64n128k16.f32.bf16.bf16 {%0,%1,%2,%3,%4,%5,%6,%7,%8,%9,%10,%11,%12,%13,%14,%15,%16,%17,%18,%19,%20,%21,%22,%23,%24,%25,%26,%27,%28,%29,%30,%31,%32,%33,%34,%35,%36,%37,%38,%39,%40,%41,%42,%43,%44,%45,%46,%47,%48,%49,%50,%51,%52,%53,%54,%55,%56,%57,%58,%59,%60,%61,%62,%63}, {%64,%65,%66,%67}, %68, p, 1, 1, %69;\n}"
   : "+f"(d[O+0]), "+f"(d[O+1]), "+f"(d[O+2]), "+f"(d[O+3]), "+f"(d[O+4]), "+f"(d[O+5]), "+f"(d[O+6]), "+f"(d[O+7]), "+f"(d[O+8]), "+f"(d[O+9]), "+f"(d[O+10]), "+f"(d[O+11]), "+f"(d[O+12]), "+f"(d[O+13]), "+f"(d[O+14]), "+f"(d[O+15]), "+f"(d[O+16]), "+f"(d[O+17]), "+f"(d[O+18]), "+f"(d[O+19]), "+f"(d[O+20]), "+f"(d[O+21]), "+f"(d[O+22]), "+f"(d[O+23]), "+f"(d[O+24]), "+f"(d[O+25]), "+f"(d[O+26]), "+f"(d[O+27]), "+f"(d[O+28]), "+f"(d[O+29]), "+f"(d[O+30]), "+f"(d[O+31]), "+f"(d[O+32]), "+f"(d[O+33]), "+f"(d[O+34]), "+f"(d[O+35]), "+f"(d[O+36]), "+f"(d[O+37]), "+f"(d[O+38]), "+f"(d[O+39]), "+f"(d[O+40]), "+f"(d[O+41]), "+f"(d[O+42]), "+f"(d[O+43]), "+f"(d[O+44]), "+f"(d[O+45]), "+f"(d[O+46]), "+f"(d[O+47]), "+f"(d[O+48]), "+f"(d[O+49]), "+f"(d[O+50]), "+f"(d[O+51]), "+f"(d[O+52]), "+f"(d[O+53]), "+f"(d[O+54]), "+f"(d[O+55]), "+f"(d[O+56]), "+f"(d[O+57]), "+f"(d[O+58]), "+f"(d[O+59]), "+f"(d[O+60]), "+f"(d[O+61]), "+f"(d[O+62]), "+f"(d[O+63])
   : "r"(a0), "r"(a1), "r"(a2), "r"(a3), "l"(db), "n"(TB), "r"(sd));
}

#define NEARLY 0
#define XAHEAD 3
#define HEADN 6
#define WBATCH 1
#define WB 8
#define WSLEEP 20
#define XSPREAD 4
#define NOSEND 0
#define MSPLIT 2
#define PFALL 1
#define L2PF 0
#define STAG 0
#define EPF 2
#define XNB 2
#define FNB 0
#define GNB 0
#define TH 4
#define PF0 4
#define FSPLIT 1
#define MGLU 1
#define SPC 2
#define TL 14
#define GKB 4
#define T0A 7
#define T0B 11
#define TGATE 1
#define ZLATE 0
#define EARLYADD 0
#define OA 3
#define OB 11
#define EB 10
#define PROMO 2
#define FB 6
#define SPACE 100
#define WPF 1
#define WAFTER 7
#define WPACE 0
#define GATE_AT 4
#define TPACE 40
#define PFMODE 0
#define MAPMODE 1
template <int V> struct IC { static constexpr int value = V; };
struct Maps { CUtensorMap x, ft, g64, u64, e, wr, wi, xs, ts, t, g32, u32, d224, fg; };

constexpr int NCTA = 130;
constexpr int U = 16384;
constexpr int TB = 36864;
constexpr int OFF_RING = 8 * U, OFF_Z = 12 * U, OFF_XB = 12 * U, OFF_T = 13 * U, OFF_D = OFF_T;
constexpr int OFF_BAR = 14 * U, OFF_SP = OFF_BAR + 512, OFF_G = OFF_SP + 1024 + 128;
constexpr int SMEM_BYTES = OFF_G + 512;
constexpr int B_FX = 0, B_FA = 8, B_FT = 12, B_Z = 16, B_W = 24, B_HX = 25, B_TL = 26, B_HP = 27, B_WR = 31;
constexpr int B_EA = 36, B_ET = 40, B_PZ = 44, B_RDY = 46, B_FE = 47;
constexpr int B_T = 51, B_XS = 52, B_G = 54, B_RD0 = 55, NBAR = 56;
__device__ __forceinline__ int srow(int rb, int r) { return 2 * rb + (r >> 6) + 32 * (r & 7) + 256 * ((r >> 4) & 3) + 1024 * ((r >> 3) & 1); }
__host__ __device__ constexpr int rslot(int n) { return n & 3; }
__host__ __device__ constexpr int rpar(int n) { return (n >> 2) & 1; }

__global__ void __cluster_dims__(2, 1, 1) __launch_bounds__(512, 1)
fused_kernel(Work* __restrict__ ws, const uint16_t* __restrict__ dtab, const __nv_bfloat16* __restrict__ w_r, const __nv_bfloat16* __restrict__ w_i,
             const __nv_bfloat16* __restrict__ gate_w, const __nv_bfloat16* __restrict__ x, __nv_bfloat16* __restrict__ out,
             const __grid_constant__ Maps maps) {
  extern __shared__ __align__(1024) uint8_t smem[];
  if (threadIdx.x < 32 && elect_one()) {
#pragma unroll
    for (int i = 0; i < PF0; i++) asm volatile("prefetch.tensormap [%0];" ::"l"((const char*)&maps + i * 128) : "memory");
  }
  const uint32_t sb = smem_u32(smem);
  const uint32_t bars = sb + OFF_BAR;
  const int tid = threadIdx.x, lane = tid & 31;
  const int warp = __shfl_sync(0xffffffffu, tid >> 5, 0);
  const bool helper = blockIdx.x >= 128;
  const int cl = (blockIdx.x >> 1) & 63, rank = blockIdx.x & 1;
  const int q4 = (cl & 1) | ((cl >> 2) & 2), rb = ((cl >> 1) & 3) | ((cl >> 4) << 2);
  const int j = 2 * q4 + rank;
  const int f_full = 448 * q4 + (rank ? 256 : 0);
  const int f_half = 448 * q4 + (rank ? 224 : 192);

  if (tid == 64) { PROF_EV(0); PROF_CK(40); }
  if (warp < 8) {
    if (!helper && tid < 32) {
      const int r = 16 * j + (tid & 15);
      asm volatile("prefetch.global.L2 [%0];" ::"l"(x + (size_t)srow(rb, r) * 512 + 64 * (tid >> 4)));
    }
    asm volatile("barrier.cluster.arrive.relaxed.aligned;" ::: "memory");
    asm volatile("setmaxnreg.inc.sync.aligned.u32 192;");
    if (!helper) {
      const int wg = warp >> 2, w = warp & 3, g = lane >> 2;
      const bool elect = (tid & 127) == 0;
      float cX[32], cD[64], cA[64], cB[64], cC[64], ci[64], ct[64];
      const int zero = blockIdx.x >> 16;
      uint32_t h[56], yf[16];
      const uint32_t d0 = (sb & 0x3FFFF) >> 4;
      const uint32_t dK = d0 | (1u << 16), dN = d0 | (512u << 16);
      const uint32_t dX = dK + wg * 512;
      constexpr uint32_t RING = OFF_RING >> 4;
      auto waitA = [&](int n) { mbar_wait(bars + 8 * (B_FA + rslot(n)), rpar(n)); };
      auto freeA = [&](int n) { mbar_arrive_if(elect, bars + 8 * (B_EA + rslot(n))); };
      auto nop = [] {};

      asm volatile("bar.sync 0, 384;" ::: "memory");
#pragma unroll 1
      for (int i = 0; i < 4; i++) {
        const uint64_t dx = d128(dX + i * 2048), df = d128(dK + (OFF_XB >> 4) + (i & 1) * 1024);
        mbar_wait(bars + 8 * (B_FX + 2 * i), 0);
        wg_fence();
        mma_ss64<0, 0, 2>(cX, df, dx, i);
        mma_ss64<0, 0, 1>(cX, df + 2, dx + 2);
        wg_commit(); wg_wait<1>();
        mbar_arrive_if(elect && i, bars + 8 * (B_EA + rslot(i - 1)));
        mma_ss64<0, 0, 1>(cX, df + 4, dx + 4);
        mma_ss64<0, 0, 1>(cX, df + 6, dx + 6);
        if (i == 0 && tid == 0) PROF_EV(1);
        mbar_wait(bars + 8 * (B_FX + 2 * i + 1), 0);
        wg_fence();
#pragma unroll
        for (int k = 0; k < 4; k++) mma_ss64<0, 0, 1>(cX, df + (512 + k * 2), dx + (1024 + k * 2));
        wg_commit();
        waitA(i);
        wg_fence();
        const uint64_t da = d128(dX + i * 1024), db = d128(dN + RING + i * 1024);
        mma_ss128<0, 1, 2>(cA, da, db, i);
        wg_commit(); wg_wait<1>();
        mbar_arrive_if(elect, bars + 8 * (B_FE + i));
#pragma unroll
        for (int k = 1; k < 4; k++) mma_ss128<0, 1, 1>(cA, da + k * 2, db + k * 128);
        wg_commit();
      }
      fence_regs<0, 32>(cX);
#pragma unroll
      for (int e = 0; e < 8; e++) {
        const int o = 8 * (e >> 1) + 2 * (e & 1);
        yf[e] = pack_pin(cX[o] + cX[o + 4], cX[o + 1] + cX[o + 5]); yf[8 + e] = pack_pin(cX[o] - cX[o + 4], cX[o + 1] - cX[o + 5]);
      }
      if (tid == 0) { PROF_EV(2); PROF_CK(42); }
      {
        waitA(4);
        const uint64_t de = d128(dN + RING + wg * 512);
        wg_fence();
        mma_rs64<0, 1, 0>(cD, yf[0], yf[1], yf[2], yf[3], de);
        mma_rs64<32, 1, 0>(cD, yf[8], yf[9], yf[10], yf[11], de + 256);
        wg_commit();
        wg_wait<1>();
        freeA(3);
        mma_rs64<0, 1, 1>(cD, yf[4], yf[5], yf[6], yf[7], de + 128);
        mma_rs64<32, 1, 1>(cD, yf[12], yf[13], yf[14], yf[15], de + 384);
        wg_commit();
      }
      bool rel = false;
      auto acquire = [&](int n) {
        rel = elect;
        if (!mbar_try(bars + 8 * (B_FA + rslot(n)), rpar(n))) { wg_wait<0>(); freeA(n - 1); rel = false; waitA(n); }
      };
      auto freeP = [&](int n) { mbar_arrive_if(rel, bars + 8 * (B_EA + rslot(n - 1))); };
      auto ffn_step = [&](auto first, auto split, float (&acc)[64], int n, int kb, auto done, auto work) {
        constexpr int SPLIT = decltype(split)::value;
        acquire(n);
        wg_fence();
        const uint64_t dx = d128(dX + kb * 1024), db = d128(dN + RING + rslot(n) * 1024);
        mma_ss128<0, 1, decltype(first)::value>(acc, dx, db, kb);
#pragma unroll
        for (int k = 1; k < SPLIT; k++) mma_ss128<0, 1, 1>(acc, dx + k * 2, db + k * 128);
        wg_commit();
        work();
        wg_wait<1>();
        freeP(n);
        done();
        if (SPLIT < 4) {
          wg_fence();
#pragma unroll
          for (int k = SPLIT; k < 4; k++) mma_ss128<0, 1, 1>(acc, dx + k * 2, db + k * 128);
          wg_commit();
        }
      };
      {
        const int s0 = 2 * rb + wg, kr = 2 * ((s0 & 1) | ((s0 & 4) >> 1));
        const int m = lane >> 3, r = lane & 7;
        const uint32_t a0 = sb + OFF_XB + wg * 8192 + ((2 * (m >> 1) + (r >> 2)) * 2 + (w & 1)) * 256 + (m & 1) * 128 + (((2 * (r & 3) + ((w >> 1) ^ (r >> 2))) ^ (kr + (m & 1))) << 4);
        ffn_step(IC<1>(), IC<4>(), cA, 5, 4, [&] { fence_regs<0, 64>(cD); }, [&] { mbar_wait(bars + 8 * (B_FE + 2), 0); });
        auto stage = [&](int i) {
          const int o = 32 * (i >> 1) + 8 * (i & 1);
          stsm4t(a0 + i * 2048, pack_bf16(cD[o] - cD[o + 18], cD[o + 1] - cD[o + 19]), pack_bf16(cD[o + 16] + cD[o + 2], cD[o + 17] + cD[o + 3]),
                 pack_bf16(cD[o + 4] - cD[o + 22], cD[o + 5] - cD[o + 23]), pack_bf16(cD[o + 20] + cD[o + 6], cD[o + 21] + cD[o + 7]));
          if (j == 0 && w == 0) {
            const uint32_t a1 = r ? sb + OFF_SP + 1024 : sb + OFF_SP + wg * 512 + (m & 1) * 256 + (m >> 1) * 128;
#pragma unroll
            for (int n = 0; n < 2; n++)
              asm volatile("stmatrix.sync.aligned.m8n8.x4.shared.b16 [%0], {%1,%2,%3,%4};" ::"r"(a1 + (((2 * i + n) ^ (kr + (m >> 1)) ^ r) << 4)),
                           "r"(pack_bf16(cD[o + 4 * n], cD[o + 4 * n + 1])), "r"(pack_bf16(cD[o + 4 * n + 2], cD[o + 4 * n + 3])),
                           "r"(pack_bf16(cD[o + 16 + 4 * n], cD[o + 17 + 4 * n])), "r"(pack_bf16(cD[o + 18 + 4 * n], cD[o + 19 + 4 * n])) : "memory");
          }
        };
        auto publish = [&] {
          asm volatile("fence.proxy.async.shared::cta;" ::: "memory");
          __syncwarp();
          mbar_arrive_if(lane == 0, bars + 8 * (B_XS + wg));
          if (tid == 0) PROF_EV(3);
        };
        stage(0);
        ffn_step(IC<1>(), IC<FSPLIT>(), cA, 6, 5, nop, nop);
        stage(1);
        ffn_step(IC<1>(), IC<FSPLIT>(), cA, 7, 6, nop, nop);
        stage(2);
        ffn_step(IC<1>(), IC<2>(), cA, 8, 7, [&] { stage(3); }, nop);
        publish();
      }
      uint32_t gb0 = 0, gb1 = 0;
      uint32_t ob[2] = {0, 0};
      auto glu = [&](auto& acc, int half, int ho, int i0, int i1) {
#pragma unroll
        for (int i = i0; i < i1; i++)
          asm volatile("{\n.reg .b32 a, b;\ncvt.rn.relu.bf16x2.f32 a, %2, %1;\ncvt.rn.bf16x2.f32 b, %4, %3;\nmul.rn.bf16x2 a, a, b;\nmul.rn.bf16x2 %0, a, %5;\n}"
                       : "=r"(h[ho + i]) : "f"(acc[2 * i]), "f"(acc[2 * i + 1]), "f"(acc[half + 2 * i]), "f"(acc[half + 1 + 2 * i]), "r"(ob[i & 1]) : "memory");
      };
      ffn_step(IC<0>(), IC<1>(), cB, 9, 0, nop, nop);
#pragma unroll 1
      for (int kb = 1; kb < 8; kb++)
        ffn_step(IC<1>(), IC<FSPLIT>(), cB, 9 + kb, kb, nop, [&] {
          if (kb == GKB) {
            mbar_wait(bars + 8 * B_G, 0);
            asm volatile("ld.shared.u32 %0, [%2];\nld.shared.u32 %1, [%2+32];" : "=r"(gb0), "=r"(gb1) : "r"(sb + OFF_G + (wg * 64 + w * 16 + g) * 4) : "memory");
          } else if (kb == 5 + 2 * wg) {
            ob[0] = pack_bf16(1.0f - bf_hi(gb0), 1.0f - bf_hi(gb0)); ob[1] = pack_bf16(1.0f - bf_hi(gb1), 1.0f - bf_hi(gb1));
            glu(cA, 32, 0, 0, 16);
          }
        });
      const uint32_t tag = gb0 & 1;
      const float g0 = bf_hi(gb0), g1 = bf_hi(gb1);
      if (tid == 0) { PROF_EV(4); PROF_CK(43); }
      auto m_step = [&](auto first, int i) {
        acquire(17 + i);
        wg_fence();
        const uint64_t dx = d128(dX + i * 2048), dm = d64(dN + RING + rslot(17 + i) * 1024);
        mma_ss64<0, 1, decltype(first)::value>(ct, dx, dm);
#pragma unroll
        for (int k = 1; k < MSPLIT; k++) mma_ss64<0, 1, 1>(ct, dx + ((k >> 2) * 1024 + (k & 3) * 2), dm + k * 64);
        wg_commit();
        wg_wait<1>();
        freeP(17 + i);
        wg_fence();
#pragma unroll
        for (int k = MSPLIT; k < 8; k++) mma_ss64<0, 1, 1>(ct, dx + ((k >> 2) * 1024 + (k & 3) * 2), dm + k * 64);
        wg_commit();
      };
      m_step(IC<0>(), 0);
#pragma unroll 1
      for (int i = 1; i < 5; i++) {
        if (i == 1 + 2 * wg) glu(cB, 32, 16, 0, 16);
        if (i < 4) m_step(IC<1>(), i);
      }
      if (tid == 0) { PROF_EV(5); PROF_CK(44); }
      ffn_step(IC<0>(), IC<1>(), cC, 21, 0, nop, nop);
#pragma unroll 1
      for (int kb = 1; kb < 8; kb++)
        ffn_step(IC<1>(), IC<FSPLIT>(), cC, 21 + kb, kb, [&] { mbar_arrive_if(elect && !(kb & 1), bars + 8 * (B_ET + (kb >> 1) - 1)); }, [&] {
          if (kb == 1 + wg) glu(ct, 16, 48, 0, 8);
        });

      auto twait = [&](uint32_t bar, uint32_t par, int) { mbar_wait(bar, par); };
      const int fo = warp * 128 + lane;
      auto fetch = [&](uint4 (&pv)[4], int z) {
        twait(bars + 8 * (z < 4 ? B_Z + 2 * z + wg : z < 6 ? B_HP + z - 4 : B_HP + 2 + wg), 0, 8 + z);
        const uint8_t* src = smem + (z < 4 ? OFF_Z - z * U : z == 4 ? OFF_T : (z - 5) * U) + fo * 16;
#pragma unroll
        for (int i = 0; i < 4; i++) pv[i] = *(const uint4*)(src + i * 512);
      };
      const uint32_t peerZ = mapa(sb + OFF_Z + fo * 16, rank ^ 1), peerB = mapa(bars + 8 * (B_Z + wg), rank ^ 1);
      auto tile_mma = [&](auto off, int t, int k0, int k1, bool fresh = false) {
        constexpr int O = decltype(off)::value;
        const uint64_t db = d128(dN + (t & 3) * (TB >> 4)), dw = db + rank * 256, dm = db + (rank ? 0 : 1536);
#pragma unroll
        for (int k = k0; k < k1; k++) {
          if (k == 0 && O == 0) mma_rs64<O, 1, 2>(ct, h[0], h[1], h[2], h[3], dw, zero);
          else if (k < 14) mma_rs64<O, 1, 1>(ct, h[4 * k], h[4 * k + 1], h[4 * k + 2], h[4 * k + 3], k < 12 ? dw + k * 128 : dm + (k - 12) * 128);
          else if (k == 14 && fresh) mma_rs64<O, 1, 0>(ct, yf[0], yf[1], yf[2], yf[3], db + k * 128);
          else if (k == 14) mma_rs64<O, 1, 2>(ct, yf[0], yf[1], yf[2], yf[3], db + k * 128, zero);
          else mma_rs64<O, 1, 1>(ct, yf[4 * k - 56], yf[4 * k - 55], yf[4 * k - 54], yf[4 * k - 53], db + k * 128);
        }
      };
      uint4 pv[4];
      const uint32_t sgn = rank ? 0x80008000u : 0u;
      auto snapshot = [&] {
        wg_wait<1>();
        fence_regs<32, 32>(ct);
#pragma unroll
        for (int i = 0; i < 4; i++)
          pv[i] = make_uint4(pack_pin(ct[32 + 8 * i], ct[33 + 8 * i]) ^ sgn, pack_pin(ct[34 + 8 * i], ct[35 + 8 * i]) ^ sgn,
                             pack_pin(ct[36 + 8 * i], ct[37 + 8 * i]) ^ sgn, pack_pin(ct[38 + 8 * i], ct[39 + 8 * i]) ^ sgn);
      };
      auto odd_head = [&](int t) {
        twait(bars + 8 * (B_FT + (t & 3)), t >> 2, t);
        wg_fence();
        tile_mma(IC<32>(), t, 0, OA);
        wg_commit();
        if (t < 4) twait(bars + 8 * (t == 1 ? B_RD0 : B_RDY), 0, 14 + t);
        wg_wait<1>();
        mbar_arrive_if(elect && t < 6, bars + 8 * (B_ET + t - 1));
        fence_regs<0, 32>(ct);
        wg_fence();
#pragma unroll
        for (int i = 0; i < 4; i++) {
          asm volatile("st.async.weak.shared::cluster.mbarrier::complete_tx::bytes.v4.b32 [%0], {%2,%3,%4,%5}, [%1];" ::"r"(peerZ - (t >> 1) * U + i * 512),
                       "r"(peerB + 16 * (t >> 1)), "r"(add_bf2(pv[i].x, pack_bf16(ct[8 * i], ct[8 * i + 1]))), "r"(add_bf2(pv[i].y, pack_bf16(ct[8 * i + 2], ct[8 * i + 3]))),
                       "r"(add_bf2(pv[i].z, pack_bf16(ct[8 * i + 4], ct[8 * i + 5]))), "r"(add_bf2(pv[i].w, pack_bf16(ct[8 * i + 6], ct[8 * i + 7]))) : "memory");
          tile_mma(IC<32>(), t, OA + i, OA + i + 1);
        }
        wg_commit();
      };
      asm volatile("barrier.cluster.wait.aligned;" ::: "memory");
      twait(bars + 8 * B_FT, 0, 0);
      wg_fence();
      tile_mma(IC<0>(), 0, 0, T0A);
      wg_commit();
      waitA(29);
      wg_wait<1>();
      mbar_arrive_if(elect, bars + 8 * (B_ET + 3));
      glu(cC, 32, 32, 0, 16);
      if (tid == 0) PROF_EV(6);
      if (tid == 128) PROF_EV(27);
      mbar_wait(bars + 8 * (j == 0 ? B_T : B_TL), 0);
      if (tid == 0) { PROF_EV(7); PROF_CK(45); }
      wg_fence();
      {
        const uint64_t dt = d128(dN + (OFF_T >> 4) + wg * 512), de = d128(dK + RING + 1024 + wg * 512);
        mma_ss64<0, 1, 0>(ci, de, dt);
        mma_ss64<32, 1, 0>(ci, de + 4, dt + 256);
        mma_ss64<0, 1, 1>(ci, de + 2, dt + 128);
        mma_ss64<32, 1, 1>(ci, de + 6, dt + 384);
        wg_commit();
      }
      tile_mma(IC<0>(), 0, T0A, T0B);
      wg_commit();
      wg_wait<1>();
      if (elect) asm volatile("mbarrier.arrive.shared::cluster.b64 _, [%0];" ::"r"(mapa(bars + 8 * B_RDY, rank ^ 1)) : "memory");
      mbar_arrive_if(elect, bars + 8 * (B_PZ + 1));
      fence_regs<0, 64>(ci);
#pragma unroll
      for (int n = 0; n < 8; n++) {
        const float s0 = g0 * (2.0f / (2048.0f * 512.0f)), s1 = g1 * (2.0f / (2048.0f * 512.0f));
        float u[4];
#pragma unroll
        for (int e = 0; e < 4; e++) {
          const int o = 32 * (e >> 1) + 4 * n + (e & 1);
          u[e] = (n & 1) ? ci[o] - ci[o - 2] : ci[o] + ci[o + 6];
        }
        yf[2 * n] = pack_pin((u[0] + u[2]) * s0, (u[1] + u[3]) * s0); yf[2 * n + 1] = pack_pin((u[0] - u[2]) * s1, (u[1] - u[3]) * s1);
      }
      wg_fence();
      tile_mma(IC<32>(), 0, 14, 18, true);
      wg_commit();
      tile_mma(IC<0>(), 0, T0B, 14);
      wg_commit();
      snapshot();
      if (tid == 0) PROF_EV(8);
      if (tid == 128) PROF_EV(28);
#pragma unroll 1
      for (int t = 1; t < 7; t += 2) {
        odd_head(t);
        wg_fence();
        tile_mma(IC<32>(), t, OA + 4, 14);
        wg_commit();
        const int zo = t >> 1, owner = rb * 8 + 2 * ((q4 + zo + 1) & 3) + rank;
        uint4* dst = ws->part + (size_t)(owner * 3 + zo) * 1024 + fo;
        uint32_t pk[16];
        auto send = [&] {
#pragma unroll
          for (int i = 0; i < 4; i++)
            asm volatile("st.relaxed.gpu.global.v4.u32 [%0], {%1,%2,%3,%4};" ::"l"(dst + i * 32), "r"((add_bf2(pv[i].x, pk[4 * i]) & ~1u) | tag),
                         "r"(add_bf2(pv[i].y, pk[4 * i + 1])), "r"(add_bf2(pv[i].z, pk[4 * i + 2])), "r"(add_bf2(pv[i].w, pk[4 * i + 3])) : "memory");
          hint_add_if(lane == 0, &ws->cntP[32 * owner + 8 * (zo + (zo == 2 ? wg : 0))]);
        };
        if (t == 5) fetch(pv, 2);
        twait(bars + 8 * (B_FT + ((t + 1) & 3)), (t + 1) >> 2, t + 1);
        wg_fence();
        tile_mma(IC<0>(), t + 1, 0, TH);
        wg_commit();
        wg_wait<1>();
        mbar_arrive_if(elect && t < 5, bars + 8 * (B_ET + t));
        fence_regs<32, 32>(ct);
#pragma unroll
        for (int i = 0; i < 16; i++) pk[i] = pack_pin(ct[32 + 2 * i], ct[33 + 2 * i]);
        if (t == 5) send();
        wg_fence();
        tile_mma(IC<32>(), t + 1, 14, 18);
        tile_mma(IC<0>(), t + 1, TH, FB);
        wg_commit();
        if (t != 5) fetch(pv, zo);
        wg_fence();
        tile_mma(IC<0>(), t + 1, FB, EB);
        wg_commit();
        if (t != 5) send();
        wg_fence();
        tile_mma(IC<0>(), t + 1, EB, 14);
        wg_commit();
        snapshot();
      }
      {
        uint4 p1[4], p2[4];
        auto acc4 = [&](uint4 (&d)[4], const uint4 (&a)[4]) {
#pragma unroll
          for (int i = 0; i < 4; i++) { d[i].x = add_bf2(d[i].x, a[i].x); d[i].y = add_bf2(d[i].y, a[i].y); d[i].z = add_bf2(d[i].z, a[i].z); d[i].w = add_bf2(d[i].w, a[i].w); }
        };
        auto add32 = [&](const uint4 (&a)[4]) {
#pragma unroll
          for (int i = 0; i < 4; i++) {
            const uint32_t u[4] = {a[i].x, a[i].y, a[i].z, a[i].w};
#pragma unroll
            for (int e = 0; e < 4; e++) { ct[32 + 8 * i + 2 * e] += bf_lo(u[e]); ct[33 + 8 * i + 2 * e] += bf_hi(u[e]); }
          }
        };
        odd_head(7);
        fetch(pv, 4);
        fetch(p1, 5);
        wg_fence();
        tile_mma(IC<32>(), 7, OA + 4, OB);
        wg_commit();
        uint32_t bad = 0;
#pragma unroll
        for (int i = 0; i < 4; i++) { bad |= (pv[i].x ^ tag) | (p1[i].x ^ tag); pv[i].x &= ~1u; p1[i].x &= ~1u; }
        acc4(pv, p1);
        fetch(p1, 3);
        wg_fence();
        tile_mma(IC<32>(), 7, OB, 14);
        wg_commit();
        if (tid == 0) { PROF_EV(9); PROF_CK(46); }
        if (tid == 128) PROF_EV(29);
        fetch(p2, 6);
        if (tid == 0) PROF_EV(24);
        wg_wait<0>();
        fence_regs<32, 32>(ct);
#pragma unroll
        for (int i = 0; i < 4; i++) bad |= p2[i].x ^ tag;
        if (__any_sync(0xffffffffu, bad & 1)) {
          const uint4* src = ws->part + (size_t)(rb * 8 + j) * 3 * 1024 + fo;
          uint4 p0[4];
          int n = 0;
          do {
            bad = 0;
#pragma unroll
            for (int i = 0; i < 4; i++) {
              pv[i] = ld_x4(src + i * 32); p0[i] = ld_x4(src + 1024 + i * 32); p2[i] = ld_x4(src + 2048 + i * 32);
              bad |= (pv[i].x ^ tag) | (p0[i].x ^ tag) | (p2[i].x ^ tag);
            }
            if (++n > (1 << 21)) __trap();
          } while (__any_sync(0xffffffffu, bad & 1));
#pragma unroll
          for (int i = 0; i < 4; i++) { pv[i].x &= ~1u; p0[i].x &= ~1u; }
          acc4(pv, p0);
        }
#pragma unroll
        for (int i = 0; i < 4; i++) p2[i].x &= ~1u;
        acc4(p1, p2);
        add32(pv); add32(p1);
#pragma unroll
        for (int i = 0; i < 4; i++)
          pv[i] = make_uint4(pack_bf16(ct[32 + 8 * i], ct[33 + 8 * i]), pack_bf16(ct[34 + 8 * i], ct[35 + 8 * i]), pack_bf16(ct[36 + 8 * i], ct[37 + 8 * i]), pack_bf16(ct[38 + 8 * i], ct[39 + 8 * i]));
        if (tid == 0) PROF_EV(14);
        const uint32_t stg = sb + OFF_T + warp * 2048;
        const int mr = (lane & 7) + ((lane >> 3) & 1) * 8, mc = lane >> 4;
#pragma unroll
        for (int i = 0; i < 4; i++)
          asm volatile("stmatrix.sync.aligned.m8n8.x4.shared.b16 [%0], {%1,%2,%3,%4};" ::"r"(stg + mr * 128 + (((2 * i + mc) ^ (mr & 7)) << 4)), "r"(pv[i].x),
                       "r"(pv[i].y), "r"(pv[i].z), "r"(pv[i].w) : "memory");
        __syncwarp();
#pragma unroll
        for (int i = 0; i < 4; i++) {
          const int r = 4 * i + (lane >> 3), c = lane & 7;
          const uint4 v = *(const uint4*)(smem + OFF_T + warp * 2048 + r * 128 + ((c ^ (r & 7)) << 4));
          *(uint4*)(out + (size_t)srow(rb, 16 * warp + r) * 512 + 64 * (q4 + 4 * rank) + 8 * c) = v;
        }
      }
      if (tid == 0) { PROF_EV(15); PROF_CK(41); }
      if (tid == 128) PROF_EV(30);
    }
  } else if (warp < 12) {
    asm volatile("setmaxnreg.dec.sync.aligned.u32 104;");
    asm volatile("barrier.cluster.arrive.relaxed.aligned;" ::: "memory");
    const int t = tid - 256, w = warp - 8;
    const uint32_t ep = ld_x1(&ws->epoch[blockIdx.x * 8]);
    const uint32_t tag = (ep + 1) & 1;
    auto w_issue = [&](const CUtensorMap* m) {

      if (elect_one()) { mbar_expect_tx(bars + 8 * (B_WR + w), 3072); tma4d(sb + OFF_T + w * 3072, m, bars + 8 * (B_WR + w), 32 * j, 0, 2 * w + (rb >> 3), rb & 7); }

          __syncwarp();
    };
    auto gate_rows = [&] {
      const int r = 16 * j + 4 * w + (lane >> 3);
      const uint4* pg = (const uint4*)gate_w + (lane & 7);
      {
        float a = 0.f;
        asm volatile("bar.sync 4, 256;" ::: "memory");
#pragma unroll 1
        for (int hf = 0; hf < 2; hf++) {
          uint4 v[4], u[4];
#pragma unroll
          for (int kb = 0; kb < 4; kb++) v[kb] = __ldg(pg + (4 * hf + kb) * 8);
          mbar_wait(bars + 8 * (B_FE + 1 + 2 * hf), 0);
          if (hf) w_issue(&maps.wr);
#pragma unroll
          for (int kb = 0; kb < 4; kb++) u[kb] = *(const uint4*)(smem + (4 * hf + kb) * U + r * 128 + (((lane ^ r) & 7) << 4));
#pragma unroll
          for (int kb = 0; kb < 4; kb++) {
            const uint32_t uu[4] = {u[kb].x, u[kb].y, u[kb].z, u[kb].w}, vv[4] = {v[kb].x, v[kb].y, v[kb].z, v[kb].w};
#pragma unroll
            for (int e = 0; e < 4; e++) {
              uint32_t pr;
              asm("mul.rn.bf16x2 %0, %1, %2;" : "=r"(pr) : "r"(uu[e]), "r"(vv[e]));
              a += bf_lo(pr) + bf_hi(pr);
            }
          }
        }
#pragma unroll
        for (int o = 4; o; o >>= 1) a += __shfl_xor_sync(0xffffffffu, a, o);
        if ((lane & 7) == 0)
          asm volatile("st.relaxed.gpu.global.u32 [%0], %1;" ::"l"(ws->gate + rb * 128 + r),
                       "r"(pack_bf16(0.f, __fdividef(1.0f, 1.0f + __expf(-bf_lo(pack_bf16(a, 0.f))))) | tag) : "memory");
        if (t == 0) PROF_EV(18);
      }
    };
    {
      const int g = lane >> 2, q = lane & 3;
      uint32_t wf[32];
      if (!helper) {
        gate_rows();
        const uint32_t wa = sb + OFF_T + w * (3072 + 4) + (rb >> 3) * 2 + q * 96 + g * 4, wb[2] = {wa + (rb & 1) * 32, wa + 32 - (rb & 1) * 32};
#pragma unroll 1
        for (int ri = 0; ri < 2; ri++) {
          mbar_wait(bars + 8 * (B_WR + w), ri);
#pragma unroll
          for (int n2 = 0; n2 < 32 / WB; n2++) {
            uint32_t v[WB];
#pragma unroll
            for (int i = 0; i < WB; i++) {
              const int e = n2 * WB + i;
              asm volatile("ld.shared.u16 %0, [%1];" : "=r"(v[i]) : "r"(wb[e & 1] + ((e >> 1) & 7) * 384 + (e >> 4) * 2) : "memory");
            }
#pragma unroll
            for (int i = 0; i < WB; i++) wf[n2 * WB + i] = __byte_perm(wf[n2 * WB + i], v[i], 0x5432);
            if (WSLEEP) { asm volatile("nanosleep.u32 %0;" ::"r"(WSLEEP + (v[WB - 1] >> 16)) : "memory"); }
          }
          __syncwarp();
          if (ri == 0) w_issue(&maps.wi);
        }
        asm volatile("bar.sync 1, 128;" ::: "memory");
        if (t == 0) PROF_EV(11);
      } else {
        asm volatile("bar.sync 4, 256;" ::: "memory");
        hint_wait(&ws->cntW[0], (ep + 1) * 128u);
        const uint32_t t0 = (uint32_t)clock();
#pragma unroll 1
        for (;;) {
          uint32_t bad = 0;
#pragma unroll
          for (int i = 0; i < 32; i++) {
            const float2 v = ld_x2((const float2*)ws->Wh + (i >> 4) * 2048 + 32 * (w & 1) + (w >> 1) + 2 * g + 16 * (i & 1) + 64 * q + ((i >> 1) & 7) * 256);
            wf[i] = __float_as_uint(v.x); bad |= __float_as_uint(v.y) ^ tag;
          }
          if (!__any_sync(0xffffffffu, bad & 1)) break;
          spin_guard(t0);
        }
        if (t == 0) PROF_EV(11);
      }
      if (w == 0 && elect_one()) { mbar_expect_tx(bars + 8 * B_W, 8192); bulk_load(sb + OFF_D, dtab, 8192, bars + 8 * B_W); }
      asm volatile("barrier.cluster.wait.aligned;" ::: "memory");
      mbar_wait(bars + 8 * B_W, 0);
      mbar_wait(bars + 8 * B_HX, 0);
      if (t == 0) PROF_EV(12);
      const uint32_t dd = (sb & 0x3FFFF) >> 4;
      const uint64_t dF = d128((dd + (OFF_D >> 4)) | (512u << 16)), dI = d128((dd + (OFF_D >> 4)) | (1u << 16)), dA = d128((dd + (OFF_XB >> 4)) | (512u << 16));
      float az[32];
      const int zero = blockIdx.x >> 16;
      uint32_t pf[32];
#pragma unroll
      for (int mt = 0; mt < 2; mt++) {
        wg_fence();
        if (mt == 0) mma_ss64<0, 3, 0>(az, dA, dF);
        else mma_ss64<0, 3, 2>(az, dA + 512, dF, zero);
#pragma unroll
        for (int k = 1; k < 4; k++) mma_ss64<0, 3, 1>(az, dA + (mt * 512 + k * 128), dF + k * 128);
        wg_commit();
        wg_wait<0>();
        fence_regs<0, 32>(az);
#pragma unroll
        for (int i = 0; i < 16; i++) {
          const float wr = bf_lo(wf[16 * mt + i]), wi = bf_hi(wf[16 * mt + i]);
          pf[16 * mt + i] = pack_pin(fmaf(az[2 * i], wr, -az[2 * i + 1] * wi), fmaf(az[2 * i], wi, az[2 * i + 1] * wr));
        }
      }
      if (t == 0) PROF_EV(16);
      {
        const int m = lane >> 3, r = lane & 7;
        const int sl = 2 * (m >> 1) + ((r >> 1) & 1) + 4 * (r >> 2);
        const uint32_t a0 = sb + OFF_XB + w * 4096 + sl * 64 + (((((m ^ rb) & 1) * 2 + (r & 1)) ^ (sl >> 1)) << 4);
        uint32_t pk[16];
#pragma unroll
        for (int mt = 0; mt < 3; mt++) {
          if (mt < 2) {
            wg_fence();
            mma_rs64<0, 0, 2>(az, pf[16 * mt], pf[16 * mt + 1], pf[16 * mt + 2], pf[16 * mt + 3], dI, mt ? (int)helper : zero);
#pragma unroll
            for (int k = 1; k < 4; k++) mma_rs64<0, 0, 1>(az, pf[16 * mt + 4 * k], pf[16 * mt + 4 * k + 1], pf[16 * mt + 4 * k + 2], pf[16 * mt + 4 * k + 3], dI + k * 2);
            wg_commit();
          }
          if (mt > 0 && !helper) {
#pragma unroll
            for (int i = 0; i < 4; i++) stsm4t(a0 + (mt - 1) * 2048 + i * 512, pk[4 * i], pk[4 * i + 1], pk[4 * i + 2], pk[4 * i + 3]);
          }
          if (mt < 2) {
            wg_wait<0>();
            fence_regs<0, 32>(az);
#pragma unroll
            for (int i = 0; i < 16; i++) pk[i] = pack_pin(az[2 * i], az[2 * i + 1]);
          }
        }
      }
      if (helper) {
#pragma unroll
        for (int i = 0; i < 16; i++) {
          const int n = i >> 1, s0 = 8 * (n >> 1) + 2 * (n & 1) + (q & 1) + 4 * (q >> 1);
          if ((n & 1) == (int)(blockIdx.x & 1)) st_u2(ws->Ts + s0 * 64 + 16 * w + g + 8 * (i & 1), pack_bf16(az[2 * i], az[2 * i + 1]), tag);
        }
        __syncwarp();
        hint_add_if(lane == 0, &ws->cntH[0]);
        if (t == 0) { ws->epoch[blockIdx.x * 8] = ep + 1; PROF_EV(13); }
      } else {
        asm volatile("fence.proxy.async.shared::cta;" ::: "memory");
        __syncwarp();
        if (elect_one()) {
          if (t == 0) PROF_EV(17);
          if (SPACE) __nanosleep(SPACE * w);
          asm volatile("cp.async.bulk.tensor.4d.global.shared::cta.bulk_group [%0, {%2, %3, %4, %5}], [%1];" ::"l"(&maps.ts), "r"(sb + OFF_XB + w * 4096),
                       "r"(32 * rank), "r"(0), "r"(2 * q4), "r"(4 * rb + w) : "memory");
          bulk_done_signal(&ws->cntT[32 * q4]);
          asm volatile("mbarrier.arrive.shared::cluster.b64 _, [%0];" ::"r"(mapa(bars + 8 * B_RD0, rank ^ 1)) : "memory");
          if (t == 96) PROF_EV(13);
        }
        __syncwarp();
        if (j == 0) {
          hint_wait(&ws->cntH[0], (ep + 1) * 8u);
          const uint32_t t0 = (uint32_t)clock();
          float2 v;
          do { v = ld_x2((const float2*)ws->Ts + 2 * rb * 64 + t); spin_guard(t0); } while (__any_sync(0xffffffffu, (__float_as_uint(v.y) ^ tag) & 1));
          mbar_wait(bars + 8 * B_TL, 0);
          const uint32_t u = __float_as_uint(v.x);
          *(uint16_t*)(smem + OFF_T + t * 128 + ((t & 7) << 4)) = (uint16_t)u;
          *(uint16_t*)(smem + OFF_T + t * 128 + (((t & 7) ^ 1) << 4)) = (uint16_t)(u >> 16);
          asm volatile("fence.proxy.async.shared::cta;" ::: "memory");
          __syncwarp();
          mbar_arrive_if(lane == 0, bars + 8 * B_T);
        }
      }
    }
  } else {
    asm volatile("setmaxnreg.dec.sync.aligned.u32 24;");
    auto xf_load = [&](int q) {
      const uint32_t fb = bars + 8 * (B_FX + q);
      mbar_expect_tx(fb, U + 8192);
      tma5d(sb + q * U, &maps.x, fb, 64 * q, 2 * rb);
      if (q >= 4) mbar_wait(bars + 8 * (B_FE + ((q - 4) >> 1)), 0);
      tma2d(sb + OFF_XB + (q & 3) * 8192, &maps.ft, fb, 64 * q, 64 * j);
    };
    if (elect_one()) {
      if (warp == 14) {
#pragma unroll
        for (int i = 0; i < B_FT; i++) mbar_init(bars + 8 * i, 1);
        asm volatile("fence.mbarrier_init.release.cluster;" ::: "memory");
        if (!helper) {
#pragma unroll 1
          for (int n = 0; n < 2; n++) {
            const uint32_t fb = bars + 8 * (B_FA + n);
            xf_load(2 * n); xf_load(2 * n + 1);
            mbar_expect_tx(fb, U);
            tma2d(sb + OFF_RING + n * U, &maps.g64, fb, f_full, 64 * n);
            tma2d(sb + OFF_RING + n * U + 8192, &maps.u64, fb, f_full, 64 * n);
          }
        }
      } else if (warp == 15) {
#pragma unroll
        for (int i = B_FT; i < NBAR; i++) mbar_init(bars + 8 * i, i < B_EA ? 1 : i < B_T ? 2 : 4);
#pragma unroll
        for (int i = 0; i < 8; i++) mbar_expect_tx(bars + 8 * (B_Z + i), U / 2);
        asm volatile("fence.mbarrier_init.release.cluster;" ::: "memory");
        asm volatile("fence.proxy.async.shared::cta;" ::: "memory");
      }
    }
    __syncwarp();
    asm volatile("bar.arrive 0, 384;" ::: "memory");
    asm volatile("bar.arrive 4, 256;" ::: "memory");
    __syncwarp();
    asm volatile("barrier.cluster.arrive.relaxed.aligned;" ::: "memory");
    asm volatile("bar.sync 3, 128;" ::: "memory");
    if (warp == 15 && !helper) {
        mbar_wait(bars + 8 * B_FE, 0);
        const uint32_t tag = (ld_x1(&ws->epoch[blockIdx.x * 8]) + 1) & 1;
        const int c = lane >> 4, jj = 16 * blockIdx.x + (lane & 15), jm = (2048 - jj) & 2047;
        const unsigned short* pr = (const unsigned short*)w_r + 256 * c;
        const unsigned short* pi = (const unsigned short*)w_i + 256 * c;
        const float wr = 0.25f * (bf_lo(__ldg(pr + jj * 257)) + bf_lo(__ldg(pr + jm * 257)));
        const float wi = 0.25f * (bf_lo(__ldg(pi + jj * 257)) - bf_lo(__ldg(pi + jm * 257)));
        st_u2(ws->Wh + c * 2048 + jj, c ? pack_bf16(-wi, wr) : pack_bf16(wr, wi), tag);
        __syncwarp();
        hint_add_if(lane == 0, &ws->cntW[0]);
        mbar_wait(bars + 8 * B_XS, 0);
        const uint32_t t0 = (uint32_t)clock();
        uint4 v;
        do { v = ld_x4(ws->gate + rb * 128 + 4 * lane); spin_guard(t0); } while (__any_sync(0xffffffffu, ((v.x ^ tag) | (v.y ^ tag) | (v.z ^ tag) | (v.w ^ tag)) & 1));
        *(uint4*)(smem + OFF_G + lane * 16) = v;
        __syncwarp();
        mbar_arrive_if(lane < 4, bars + 8 * B_G);
      }
    auto part_load = [&](int i, unsigned ep1) {
      const uint32_t bytes = i < 2 ? U : U / 2;
      mbar_wait(bars + 8 * (B_PZ + (i == 0)), 0);
      mbar_expect_tx(bars + 8 * (B_HP + i), bytes);
      flag_wait(&ws->cntP[32 * (rb * 8 + j) + 8 * i], ep1 * (i < 2 ? 8u : 4u));
      bulk_load(sb + (i == 0 ? OFF_T : i == 1 ? 0 : i * (U / 2)), ws->part + (size_t)(rb * 8 + j) * 3072 + (i < 2 ? i * 1024 : 1024 + i * 512), bytes, bars + 8 * (B_HP + i));
      if (i == 2) PROF_EV(26);
    };
    if ((!helper || warp == 15) && elect_one()) {
      if (warp < 14) {
        const int p = warp - 12;
#pragma unroll 1
        for (int i = 4 + p; i < 14; i += 2) asm volatile("prefetch.tensormap [%0];" ::"l"((const char*)&maps + i * 128) : "memory");
#pragma unroll 1
        for (int n = 2; n < 30; n++) {
          const bool table = n == 4 || n == 29;
          const bool half = n >= 17 && n < 21;
          const int q = n < 4 ? n : n < 17 ? n - 1 : n - 5;
          const CUtensorMap* m = table ? &maps.e : half ? &maps.g32 + p : &maps.g64 + p;
          const int c0 = table ? 0 : half ? f_half : f_full + 64 * (q >> 3);
          const int c1 = table ? (n & 1) * 2048 + (2 * rb + p) * 64 : half ? 128 * (n - 17) : 64 * (q & 7);
          const uint32_t fb = bars + 8 * (B_FA + (n & 3)), dst = sb + OFF_RING + (n & 3) * U + p * 8192;
          if (n < 4) mbar_wait(bars + 8 * (B_FE + n - 2), 0);
          else mbar_wait(bars + 8 * (B_EA + (n & 3)), ((n >> 2) & 1) ^ 1);
          tma2d(dst, m, fb, c0, c1);
          if (p == 0) mbar_expect_tx(fb, U);
        }
        part_load(2 + p, ld_x1(&ws->epoch[blockIdx.x * 8]) + 1);
      } else if (warp == 15) {
        const unsigned ep1 = ld_x1(&ws->epoch[blockIdx.x * 8]) + 1;
        flag_wait(&ws->cntX[helper ? 0 : 32 * j], ep1 * 16u);
        PROF_EV(22);
        mbar_expect_tx(bars + 8 * B_HX, U);
        bulk_load(sb + OFF_XB, ws->X + (size_t)(helper ? 128 : 16 * j + rb) * 8192, U, bars + 8 * B_HX);
        if (!helper) {
          flag_wait(&ws->cntT[32 * q4], ep1 * 128u);
          PROF_EV(23);
          mbar_expect_tx(bars + 8 * B_TL, U);
          tma3d(sb + OFF_T, &maps.t, bars + 8 * B_TL, 64 * j, 0, 2 * rb);
          part_load(0, ep1); part_load(1, ep1);
          mbar_wait(bars + 8 * (B_HP + 2), 0); mbar_wait(bars + 8 * (B_HP + 3), 0);
          ws->epoch[blockIdx.x * 8] = ep1;
        }
      } else {
#pragma unroll 1
        for (int q = 4; q < 8; q++) xf_load(q);
#pragma unroll 1
        for (int h2 = 0; h2 < 2; h2++) {
          const int s0 = 2 * rb + h2, sg = (s0 & ~6) | ((s0 & 2) << 1) | ((s0 & 4) >> 1);
          mbar_wait(bars + 8 * (B_XS + h2), 0);
#pragma unroll 1
          for (int c = 0; c < 2; c++) {
            asm volatile("cp.async.bulk.tensor.4d.global.shared::cta.bulk_group [%0, {%2, %3, %4, %5}], [%1];" ::"l"(&maps.xs),
                         "r"(sb + OFF_XB + h2 * 8192 + c * 4096), "r"(0), "r"(sg), "r"(0), "r"(16 * j + 8 * c) : "memory");
            if (j == 0)
              asm volatile("cp.async.bulk.global.shared::cta.bulk_group [%0], [%1], 256;" ::"l"(ws->X + 128 * 8192 + c * 4096 + sg * 128),
                           "r"(sb + OFF_SP + h2 * 512 + c * 256) : "memory");
            if (SPACE && h2 + c < 2) __nanosleep(SPACE);
          }
        }
        bulk_done_signal(&ws->cntX[32 * j]);
        PROF_EV(20);
#pragma unroll 1
        for (int t = 0; t < 8; t++) {
          const int col = 64 * (((q4 + 1 + (t >> 1)) & 3) + 4 * ((t & 1) ? rank : 1 - rank));
          const uint32_t fb = bars + 8 * (B_FT + (t & 3)), dst = sb + (t & 3) * TB;
          mbar_wait(bars + 8 * (B_ET + (t < 3 ? t + 1 : t & 3)), t >> 2);
          mbar_expect_tx(fb, (t & 1) ? 28672 : TB);
          tma2d(dst, &maps.d224, fb, col, 224 * j);
          if (!(t & 1)) tma3d(dst + 28672, &maps.fg, fb, col ^ 256, 16 * rank, 4 * q4);
        }
      }
    }
  }
}

typedef CUresult (*EncodeFn)(CUtensorMap*, CUtensorMapDataType, cuuint32_t, void*, const cuuint64_t*, const cuuint64_t*, const cuuint32_t*,
                             const cuuint32_t*, CUtensorMapInterleave, CUtensorMapSwizzle, CUtensorMapL2promotion, CUtensorMapFloatOOBfill);

static void encode(EncodeFn f, CUtensorMap* m, const void* base, int rank, const cuuint64_t* dims, const cuuint64_t* strides, const cuuint32_t* box,
                   CUtensorMapSwizzle sw) {
  cuuint32_t es[5] = {1, 1, 1, 1, 1};
  f(m, CU_TENSOR_MAP_DATA_TYPE_BFLOAT16, rank, (void*)base, dims, strides, box, es, CU_TENSOR_MAP_INTERLEAVE_NONE, sw,
    (CUtensorMapL2promotion)PROMO, CU_TENSOR_MAP_FLOAT_OOB_FILL_NONE);
}

extern "C" void kernel_launch(void* const* d_in, const int* in_sizes, int n_in, void* d_out, int out_size) {
  (void)in_sizes; (void)n_in; (void)out_size;
  const __nv_bfloat16* x = (const __nv_bfloat16*)d_in[0];
  const __nv_bfloat16* w_r = (const __nv_bfloat16*)d_in[1];
  const __nv_bfloat16* w_i = (const __nv_bfloat16*)d_in[2];
  const __nv_bfloat16* Wg = (const __nv_bfloat16*)d_in[4];
  const __nv_bfloat16* Wu = (const __nv_bfloat16*)d_in[5];
  const __nv_bfloat16* Wd = (const __nv_bfloat16*)d_in[6];
  const __nv_bfloat16* gw = (const __nv_bfloat16*)d_in[7];

  void* fp = nullptr; cudaDriverEntryPointQueryResult qr;
  cudaGetDriverEntryPoint("cuTensorMapEncodeTiled", &fp, cudaEnableDefault, &qr);
  EncodeFn enc = (EncodeFn)fp;
  void *pFT, *pET, *pDT, *pW;
  cudaGetSymbolAddress(&pDT, g_DT); cudaGetSymbolAddress(&pW, g_work);
  void *pX = ((Work*)pW)->X, *pT = ((Work*)pW)->T;
  cudaGetSymbolAddress(&pFT, g_FT); cudaGetSymbolAddress(&pET, g_ET);

  Maps mp;
  const CUtensorMapSwizzle S128 = CU_TENSOR_MAP_SWIZZLE_128B, S64 = CU_TENSOR_MAP_SWIZZLE_64B;
  { cuuint64_t d[5] = {512, 8, 2, 4, 32}, s[4] = {32768, 1048576, 262144, 1024}; cuuint32_t b[5] = {64, 8, 2, 4, 2}; encode(enc, &mp.x, x, 5, d, s, b, S128); }
  { cuuint64_t d[2] = {512, 512}, s[1] = {1024}; cuuint32_t b[2] = {64, 64}; encode(enc, &mp.ft, pFT, 2, d, s, b, S128); }
  { cuuint64_t d[4] = {128, 32, 2, 129}, s[3] = {256, 8192, 16384}; cuuint32_t b[4] = {128, 1, 2, 8}; encode(enc, &mp.xs, pX, 4, d, s, b, CU_TENSOR_MAP_SWIZZLE_NONE); }
  { cuuint64_t d[4] = {64, 32, 8, 64}, s[3] = {65536, 128, 1024}; cuuint32_t b[4] = {32, 32, 2, 1}; encode(enc, &mp.ts, pT, 4, d, s, b, S64); }
  { cuuint64_t d[3] = {512, 32, 16}, s[2] = {1024, 32768}; cuuint32_t b[3] = {64, 16, 4}; encode(enc, &mp.fg, pFT, 3, d, s, b, S128); }
  { cuuint64_t d[3] = {512, 64, 32}, s[2] = {1024, 65536}; cuuint32_t b[3] = {64, 64, 2}; encode(enc, &mp.t, pT, 3, d, s, b, S128); }
  { cuuint64_t d[2] = {64, 4096}, s[1] = {128}; cuuint32_t b[2] = {64, 64}; encode(enc, &mp.e, pET, 2, d, s, b, S128); }
  { cuuint64_t d[2] = {1792, 512}, s[1] = {3584}; cuuint32_t b[2] = {64, 64}, b2[2] = {32, 128};
    encode(enc, &mp.g64, Wg, 2, d, s, b, S128); encode(enc, &mp.u64, Wu, 2, d, s, b, S128);
    encode(enc, &mp.g32, Wg, 2, d, s, b2, S64); encode(enc, &mp.u32, Wu, 2, d, s, b2, S64); }
  { cuuint64_t d[2] = {512, 1792}, s[1] = {1024}; cuuint32_t b[2] = {64, 224}; encode(enc, &mp.d224, Wd, 2, d, s, b, S128); }
  { cuuint64_t d[4] = {264, 32, 8, 8}, s[3] = {32896, 512, 4112}; cuuint32_t b[4] = {48, 32, 1, 1};
    encode(enc, &mp.wr, w_r, 4, d, s, b, CU_TENSOR_MAP_SWIZZLE_NONE); encode(enc, &mp.wi, w_i, 4, d, s, b, CU_TENSOR_MAP_SWIZZLE_NONE); }

  cudaFuncSetAttribute(fused_kernel, cudaFuncAttributeMaxDynamicSharedMemorySize, SMEM_BYTES);
  fused_kernel<<<NCTA, 512, SMEM_BYTES>>>((Work*)pW, (const uint16_t*)pDT, w_r, w_i, gw, x, (__nv_bfloat16*)d_out, mp);
}
```

```cpp
#include <cuda_runtime.h>
#include <cuda_bf16.h>
#include <cuda.h>
#include <stdint.h>

namespace tbl {
constexpr double PI = 3.14159265358979323846264338327950288;
constexpr double sin_s(double x) { double t = x, s = x; for (int n = 1; n < 12; n++) { t *= -x * x / ((2 * n) * (2 * n + 1)); s += t; } return s; }
constexpr double cos_s(double x) { double t = 1, s = 1; for (int n = 1; n < 12; n++) { t *= -x * x / ((2 * n - 1) * (2 * n)); s += t; } return s; }
constexpr double cos2048(int m) {
  m &= 2047; if (m > 1024) m = 2048 - m;
  bool neg = false; if (m > 512) { m = 1024 - m; neg = true; }
  double v = (m <= 256) ? cos_s(2 * PI * m / 2048) : sin_s(2 * PI * (512 - m) / 2048);
  return neg ? -v : v;
}
constexpr uint16_t to_bf16(double v) {
  if (v == 0) return 0;
  uint16_t s = 0; if (v < 0) { s = 0x8000; v = -v; }
  int e = 0; while (v >= 2) { v /= 2; e++; } while (v < 1) { v *= 2; e--; }
  double m = (v - 1) * 128; int mi = (int)m; double fr = m - mi;
  if (fr > 0.5 || (fr == 0.5 && (mi & 1))) mi++;
  if (mi == 128) { mi = 0; e++; }
  return (uint16_t)(s | ((e + 127) << 7) | mi);
}
struct CosT { uint16_t v[2048]; constexpr CosT() : v() { for (int i = 0; i < 2048; i++) v[i] = to_bf16(cos2048(i)); } };
struct alignas(1024) FT {
  uint16_t v[512 * 512];
  constexpr FT() : v() {
    CosT c;
    for (int r = 0; r < 512; r++) {
      int k = (r >> 5) * 16 + 2 * (r & 7) + ((r >> 4) & 1), e = (r >> 3) & 1;
      int mul = 4 * k, add = e ? 512 : 0;
      if (k == 0 && e == 1) { mul = 1024; add = 0; }
      for (int d = 0; d < 512; d++) v[r * 512 + d] = c.v[(d * mul + add) & 2047];
    }
  }
};
struct alignas(1024) ET {
  uint16_t v[2 * 32 * 4096];
  constexpr ET() : v() {
    CosT c;
    for (int s = 0; s < 1024; s++)
      for (int j1 = 0; j1 < 64; j1++)
        for (int e = 0; e < 2; e++) {
          const int s0 = s & 31, i = s >> 5, p = j1 & 1, j = j1 >> 1;
          const uint16_t x = c.v[(s * j1 + 512 * e) & 2047];
          v[s0 * 4096 + (p * 32 + i) * 64 + e * 32 + j] = x;
          v[(32 + s0) * 4096 + ((i >> 3) * 16 + e * 8 + (i & 7)) * 64 + p * 32 + j] = x;
        }
  }
};
struct alignas(1024) DT {
  uint16_t v[64 * 64];
  constexpr DT() : v() {
    CosT c;
    for (int r = 0; r < 64; r++)
      for (int n = 0; n < 64; n++) {
        const int sg = r >> 1, s0 = (sg & ~6) | ((sg & 2) << 1) | ((sg & 4) >> 1), e = r & 1, f = n & 1;
        const int m = 64 * s0 * (n >> 1) + (e == f ? 0 : e ? -512 : 512);
        v[r * 64 + (((n >> 3) ^ (r & 7)) << 3) + (n & 7)] = c.v[m & 2047];
      }
  }
};
}

__device__ constexpr tbl::FT g_FT = tbl::FT();
__device__ constexpr tbl::ET g_ET = tbl::ET();
__device__ constexpr tbl::DT g_DT = tbl::DT();

struct alignas(1024) Work {
  unsigned epoch[132 * 8];
  unsigned cntX[8 * 32], cntT[8 * 32], cntP[128 * 32], cntW[32], cntH[32];
  alignas(16) float gate[16 * 128];
  alignas(16) uint2 Wh[2 * 2048];
  alignas(16) uint2 Ts[32 * 64];
  alignas(1024) uint16_t X[129 * 8192];
  alignas(1024) uint16_t T[32 * 64 * 512];
  alignas(1024) uint4 part[128 * 3 * 1024];
};
__device__ Work g_work;

__device__ __forceinline__ uint32_t smem_u32(const void* p) { return (uint32_t)__cvta_generic_to_shared(p); }
__device__ __forceinline__ void mbar_init(uint32_t bar, uint32_t cnt) { asm volatile("mbarrier.init.shared::cta.b64 [%0], %1;" ::"r"(bar), "r"(cnt)); }
__device__ __forceinline__ void mbar_expect_tx(uint32_t bar, uint32_t bytes) { asm volatile("mbarrier.arrive.expect_tx.shared::cta.b64 _, [%0], %1;" ::"r"(bar), "r"(bytes) : "memory"); }
__device__ __forceinline__ void mbar_arrive(uint32_t bar) { asm volatile("mbarrier.arrive.shared::cta.b64 _, [%0];" ::"r"(bar) : "memory"); }
__device__ __forceinline__ bool elect_one() {
  uint32_t p;
  asm volatile("{\n.reg .pred p;\nelect.sync _|p, 0xffffffff;\nselp.u32 %0, 1, 0, p;\n}" : "=r"(p));
  return p;
}
__device__ __forceinline__ void mbar_arrive_if(bool p, uint32_t bar) {
  asm volatile("{\n.reg .pred p;\nsetp.ne.b32 p, %1, 0;\n@p mbarrier.arrive.shared::cta.b64 _, [%0];\n}" ::"r"(bar), "r"((int)p) : "memory");
}
__device__ __forceinline__ void hint_add_if(bool p, unsigned* a) {
  asm volatile("{\n.reg .pred p;\nsetp.ne.b32 p, %1, 0;\n@p red.relaxed.gpu.global.add.u32 [%0], 1;\n}" ::"l"(a), "r"((int)p) : "memory");
}
__device__ __forceinline__ bool mbar_try(uint32_t bar, uint32_t parity) {
  uint32_t ok;
  asm volatile("{\n.reg .pred p;\nmbarrier.test_wait.parity.shared::cta.b64 p, [%1], %2;\nselp.u32 %0, 1, 0, p;\n}" : "=r"(ok) : "r"(bar), "r"(parity) : "memory");
  return ok;
}
__device__ __forceinline__ void mbar_wait(uint32_t bar, uint32_t parity) {
  asm volatile(
      "{\n.reg .pred p;\n.reg .u32 n;\nmov.u32 n, 0;\n"
      "W_LOOP:\nmbarrier.try_wait.parity.shared::cta.b64 p, [%0], %1;\n@p bra W_DONE;\n"
      "add.u32 n, n, 1;\nsetp.lt.u32 p, n, 0x40000;\n@p bra W_LOOP;\ntrap;\nW_DONE:\n}" ::"r"(bar), "r"(parity) : "memory");
}
__device__ __forceinline__ void bulk_load(uint32_t dst, const void* src, uint32_t bytes, uint32_t bar) {
  asm volatile("cp.async.bulk.shared::cluster.global.mbarrier::complete_tx::bytes [%0], [%1], %2, [%3];" ::"r"(dst), "l"(src), "r"(bytes), "r"(bar) : "memory");
}
__device__ __forceinline__ void spin_guard(uint32_t t0) { if ((uint32_t)clock() - t0 > (1u << 30)) __trap(); }
__device__ __forceinline__ float2 ld_x2(const float2* p) { float2 v; asm volatile("ld.relaxed.gpu.global.v2.f32 {%0,%1}, [%2];" : "=f"(v.x), "=f"(v.y) : "l"(p) : "memory"); return v; }
__device__ __forceinline__ void st_u2(uint2* p, uint32_t a, uint32_t b) { asm volatile("st.relaxed.gpu.global.v2.u32 [%0], {%1,%2};" ::"l"(p), "r"(a), "r"(b) : "memory"); }
__device__ __forceinline__ uint32_t ld_x1(const void* p) { uint32_t v; asm volatile("ld.relaxed.gpu.global.u32 %0, [%1];" : "=r"(v) : "l"(p) : "memory"); return v; }
__device__ __forceinline__ uint4 ld_x4(const void* p) { uint4 v; asm volatile("ld.relaxed.gpu.global.v4.u32 {%0,%1,%2,%3}, [%4];" : "=r"(v.x), "=r"(v.y), "=r"(v.z), "=r"(v.w) : "l"(p) : "memory"); return v; }
__device__ __forceinline__ uint32_t mapa(uint32_t a, uint32_t cta) { uint32_t r; asm volatile("mapa.shared::cluster.u32 %0, %1, %2;" : "=r"(r) : "r"(a), "r"(cta)); return r; }
__device__ __forceinline__ void stsm4t(uint32_t a, uint32_t r0, uint32_t r1, uint32_t r2, uint32_t r3) {
  asm volatile("stmatrix.sync.aligned.m8n8.x4.trans.shared.b16 [%0], {%1,%2,%3,%4};" ::"r"(a), "r"(r0), "r"(r1), "r"(r2), "r"(r3) : "memory");
}
__device__ __forceinline__ void hint_add(unsigned* p) { asm volatile("red.relaxed.gpu.global.add.u32 [%0], 1;" ::"l"(p) : "memory"); }
__device__ __forceinline__ void hint_wait(const unsigned* p, unsigned target) {
  const uint32_t t0 = (uint32_t)clock();
  while ((int)(ld_x1(p) - target) < 0) spin_guard(t0);
}
__device__ __forceinline__ void bulk_done_signal(unsigned* p) {
  asm volatile("cp.async.bulk.commit_group;\ncp.async.bulk.wait_group 0;\nfence.proxy.async.global;" ::: "memory");
  hint_add(p);
}
__device__ __forceinline__ void flag_wait(const unsigned* p, unsigned target) {
  hint_wait(p, target);
  asm volatile("fence.proxy.async.global;" ::: "memory");
}
__device__ __forceinline__ void tma2d(uint32_t dst, const CUtensorMap* m, uint32_t bar, int c0, int c1) {
  asm volatile("cp.async.bulk.tensor.2d.shared::cluster.global.mbarrier::complete_tx::bytes [%0], [%1, {%3, %4}], [%2];" ::"r"(dst), "l"(m), "r"(bar), "r"(c0), "r"(c1) : "memory");
}
__device__ __forceinline__ void tma3d(uint32_t dst, const CUtensorMap* m, uint32_t bar, int c0, int c1, int c2) {
  asm volatile("cp.async.bulk.tensor.3d.shared::cluster.global.mbarrier::complete_tx::bytes [%0], [%1, {%3, %4, %5}], [%2];" ::"r"(dst), "l"(m), "r"(bar), "r"(c0), "r"(c1), "r"(c2) : "memory");
}
__device__ __forceinline__ void tma4d(uint32_t dst, const CUtensorMap* m, uint32_t bar, int c0, int c1, int c2, int c3) {
  asm volatile("cp.async.bulk.tensor.4d.shared::cluster.global.mbarrier::complete_tx::bytes [%0], [%1, {%3, %4, %5, %6}], [%2];" ::"r"(dst), "l"(m), "r"(bar), "r"(c0), "r"(c1), "r"(c2), "r"(c3) : "memory");
}
__device__ __forceinline__ void tma5d(uint32_t dst, const CUtensorMap* m, uint32_t bar, int c0, int c4) {
  asm volatile("cp.async.bulk.tensor.5d.shared::cluster.global.mbarrier::complete_tx::bytes [%0], [%1, {%3, %5, %5, %5, %4}], [%2];" ::"r"(dst), "l"(m), "r"(bar), "r"(c0), "r"(c4), "r"(0) : "memory");
}
__device__ __forceinline__ void wg_fence() { asm volatile("wgmma.fence.sync.aligned;" ::: "memory"); }
__device__ __forceinline__ void wg_commit() { asm volatile("wgmma.commit_group.sync.aligned;" ::: "memory"); }
template <int N> __device__ __forceinline__ void wg_wait() { asm volatile("wgmma.wait_group.sync.aligned %0;" ::"n"(N) : "memory"); }
template <int O, int N, int NN> __device__ __forceinline__ void fence_regs(float (&d)[NN]) {
#pragma unroll
  for (int i = 0; i < N; i++) asm volatile("" : "+f"(d[O + i])::"memory");
}
__device__ __forceinline__ uint32_t pack_bf16(float lo, float hi) {
  uint32_t r; asm("cvt.rn.bf16x2.f32 %0, %1, %2;" : "=r"(r) : "f"(hi), "f"(lo)); return r;
}
__device__ __forceinline__ uint32_t pack_pin(float lo, float hi) {
  uint32_t r; asm volatile("cvt.rn.bf16x2.f32 %0, %1, %2;" : "=r"(r) : "f"(hi), "f"(lo) : "memory"); return r;
}
__device__ __forceinline__ uint32_t add_bf2(uint32_t a, uint32_t b) { uint32_t r; asm("add.rn.bf16x2 %0, %1, %2;" : "=r"(r) : "r"(a), "r"(b)); return r; }
__device__ __forceinline__ float bf_lo(uint32_t u) { return __uint_as_float(u << 16); }
__device__ __forceinline__ float bf_hi(uint32_t u) { return __uint_as_float(u & 0xffff0000u); }

__device__ __forceinline__ uint64_t d128(uint32_t lo) { uint64_t d; asm("mov.b64 %0, {%1, 0x40000040};" : "=l"(d) : "r"(lo)); return d; }
__device__ __forceinline__ uint64_t d64(uint32_t lo) { uint64_t d; asm("mov.b64 %0, {%1, 0x80000020};" : "=l"(d) : "r"(lo)); return d; }
template<int O,int TB,int ACC,int NN> __device__ __forceinline__ void mma_ss64(float (&d)[NN], uint64_t da, uint64_t db, int sd = 0){
  if constexpr (ACC == 1) asm volatile("wgmma.mma_async.sync.aligned.m64n64k16.f32.bf16.bf16 {%0,%1,%2,%3,%4,%5,%6,%7,%8,%9,%10,%11,%12,%13,%14,%15,%16,%17,%18,%19,%20,%21,%22,%23,%24,%25,%26,%27,%28,%29,%30,%31}, %32, %33, 1, 1, 1, %35, %34;"
   : "+f"(d[O+0]), "+f"(d[O+1]), "+f"(d[O+2]), "+f"(d[O+3]), "+f"(d[O+4]), "+f"(d[O+5]), "+f"(d[O+6]), "+f"(d[O+7]), "+f"(d[O+8]), "+f"(d[O+9]), "+f"(d[O+10]), "+f"(d[O+11]), "+f"(d[O+12]), "+f"(d[O+13]), "+f"(d[O+14]), "+f"(d[O+15]), "+f"(d[O+16]), "+f"(d[O+17]), "+f"(d[O+18]), "+f"(d[O+19]), "+f"(d[O+20]), "+f"(d[O+21]), "+f"(d[O+22]), "+f"(d[O+23]), "+f"(d[O+24]), "+f"(d[O+25]), "+f"(d[O+26]), "+f"(d[O+27]), "+f"(d[O+28]), "+f"(d[O+29]), "+f"(d[O+30]), "+f"(d[O+31])
   : "l"(da), "l"(db), "n"(TB & 1), "n"(TB >> 1));
  else if constexpr (ACC == 0) asm volatile("wgmma.mma_async.sync.aligned.m64n64k16.f32.bf16.bf16 {%0,%1,%2,%3,%4,%5,%6,%7,%8,%9,%10,%11,%12,%13,%14,%15,%16,%17,%18,%19,%20,%21,%22,%23,%24,%25,%26,%27,%28,%29,%30,%31}, %32, %33, 0, 1, 1, %35, %34;"
   : "=f"(d[O+0]), "=f"(d[O+1]), "=f"(d[O+2]), "=f"(d[O+3]), "=f"(d[O+4]), "=f"(d[O+5]), "=f"(d[O+6]), "=f"(d[O+7]), "=f"(d[O+8]), "=f"(d[O+9]), "=f"(d[O+10]), "=f"(d[O+11]), "=f"(d[O+12]), "=f"(d[O+13]), "=f"(d[O+14]), "=f"(d[O+15]), "=f"(d[O+16]), "=f"(d[O+17]), "=f"(d[O+18]), "=f"(d[O+19]), "=f"(d[O+20]), "=f"(d[O+21]), "=f"(d[O+22]), "=f"(d[O+23]), "=f"(d[O+24]), "=f"(d[O+25]), "=f"(d[O+26]), "=f"(d[O+27]), "=f"(d[O+28]), "=f"(d[O+29]), "=f"(d[O+30]), "=f"(d[O+31])
   : "l"(da), "l"(db), "n"(TB & 1), "n"(TB >> 1));
  else asm volatile("{\n.reg .pred p;\nsetp.ne.b32 p, %36, 0;\nwgmma.mma_async.sync.aligned.m64n64k16.f32.bf16.bf16 {%0,%1,%2,%3,%4,%5,%6,%7,%8,%9,%10,%11,%12,%13,%14,%15,%16,%17,%18,%19,%20,%21,%22,%23,%24,%25,%26,%27,%28,%29,%30,%31}, %32, %33, p, 1, 1, %35, %34;\n}"
   : "+f"(d[O+0]), "+f"(d[O+1]), "+f"(d[O+2]), "+f"(d[O+3]), "+f"(d[O+4]), "+f"(d[O+5]), "+f"(d[O+6]), "+f"(d[O+7]), "+f"(d[O+8]), "+f"(d[O+9]), "+f"(d[O+10]), "+f"(d[O+11]), "+f"(d[O+12]), "+f"(d[O+13]), "+f"(d[O+14]), "+f"(d[O+15]), "+f"(d[O+16]), "+f"(d[O+17]), "+f"(d[O+18]), "+f"(d[O+19]), "+f"(d[O+20]), "+f"(d[O+21]), "+f"(d[O+22]), "+f"(d[O+23]), "+f"(d[O+24]), "+f"(d[O+25]), "+f"(d[O+26]), "+f"(d[O+27]), "+f"(d[O+28]), "+f"(d[O+29]), "+f"(d[O+30]), "+f"(d[O+31])
   : "l"(da), "l"(db), "n"(TB & 1), "n"(TB >> 1), "r"(sd));
}
template<int O,int TB,int ACC,int NN> __device__ __forceinline__ void mma_rs64(float (&d)[NN], uint32_t a0, uint32_t a1, uint32_t a2, uint32_t a3, uint64_t db, int sd = 0){
  if constexpr (ACC == 1) asm volatile("wgmma.mma_async.sync.aligned.m64n64k16.f32.bf16.bf16 {%0,%1,%2,%3,%4,%5,%6,%7,%8,%9,%10,%11,%12,%13,%14,%15,%16,%17,%18,%19,%20,%21,%22,%23,%24,%25,%26,%27,%28,%29,%30,%31}, {%32,%33,%34,%35}, %36, 1, 1, 1, %37;"
   : "+f"(d[O+0]), "+f"(d[O+1]), "+f"(d[O+2]), "+f"(d[O+3]), "+f"(d[O+4]), "+f"(d[O+5]), "+f"(d[O+6]), "+f"(d[O+7]), "+f"(d[O+8]), "+f"(d[O+9]), "+f"(d[O+10]), "+f"(d[O+11]), "+f"(d[O+12]), "+f"(d[O+13]), "+f"(d[O+14]), "+f"(d[O+15]), "+f"(d[O+16]), "+f"(d[O+17]), "+f"(d[O+18]), "+f"(d[O+19]), "+f"(d[O+20]), "+f"(d[O+21]), "+f"(d[O+22]), "+f"(d[O+23]), "+f"(d[O+24]), "+f"(d[O+25]), "+f"(d[O+26]), "+f"(d[O+27]), "+f"(d[O+28]), "+f"(d[O+29]), "+f"(d[O+30]), "+f"(d[O+31])
   : "r"(a0), "r"(a1), "r"(a2), "r"(a3), "l"(db), "n"(TB));
  else if constexpr (ACC == 0) asm volatile("wgmma.mma_async.sync.aligned.m64n64k16.f32.bf16.bf16 {%0,%1,%2,%3,%4,%5,%6,%7,%8,%9,%10,%11,%12,%13,%14,%15,%16,%17,%18,%19,%20,%21,%22,%23,%24,%25,%26,%27,%28,%29,%30,%31}, {%32,%33,%34,%35}, %36, 0, 1, 1, %37;"
   : "=f"(d[O+0]), "=f"(d[O+1]), "=f"(d[O+2]), "=f"(d[O+3]), "=f"(d[O+4]), "=f"(d[O+5]), "=f"(d[O+6]), "=f"(d[O+7]), "=f"(d[O+8]), "=f"(d[O+9]), "=f"(d[O+10]), "=f"(d[O+11]), "=f"(d[O+12]), "=f"(d[O+13]), "=f"(d[O+14]), "=f"(d[O+15]), "=f"(d[O+16]), "=f"(d[O+17]), "=f"(d[O+18]), "=f"(d[O+19]), "=f"(d[O+20]), "=f"(d[O+21]), "=f"(d[O+22]), "=f"(d[O+23]), "=f"(d[O+24]), "=f"(d[O+25]), "=f"(d[O+26]), "=f"(d[O+27]), "=f"(d[O+28]), "=f"(d[O+29]), "=f"(d[O+30]), "=f"(d[O+31])
   : "r"(a0), "r"(a1), "r"(a2), "r"(a3), "l"(db), "n"(TB));
  else asm volatile("{\n.reg .pred p;\nsetp.ne.b32 p, %38, 0;\nwgmma.mma_async.sync.aligned.m64n64k16.f32.bf16.bf16 {%0,%1,%2,%3,%4,%5,%6,%7,%8,%9,%10,%11,%12,%13,%14,%15,%16,%17,%18,%19,%20,%21,%22,%23,%24,%25,%26,%27,%28,%29,%30,%31}, {%32,%33,%34,%35}, %36, p, 1, 1, %37;\n}"
   : "+f"(d[O+0]), "+f"(d[O+1]), "+f"(d[O+2]), "+f"(d[O+3]), "+f"(d[O+4]), "+f"(d[O+5]), "+f"(d[O+6]), "+f"(d[O+7]), "+f"(d[O+8]), "+f"(d[O+9]), "+f"(d[O+10]), "+f"(d[O+11]), "+f"(d[O+12]), "+f"(d[O+13]), "+f"(d[O+14]), "+f"(d[O+15]), "+f"(d[O+16]), "+f"(d[O+17]), "+f"(d[O+18]), "+f"(d[O+19]), "+f"(d[O+20]), "+f"(d[O+21]), "+f"(d[O+22]), "+f"(d[O+23]), "+f"(d[O+24]), "+f"(d[O+25]), "+f"(d[O+26]), "+f"(d[O+27]), "+f"(d[O+28]), "+f"(d[O+29]), "+f"(d[O+30]), "+f"(d[O+31])
   : "r"(a0), "r"(a1), "r"(a2), "r"(a3), "l"(db), "n"(TB), "r"(sd));
}
template<int O,int TB,int ACC,int NN> __device__ __forceinline__ void mma_ss128(float (&d)[NN], uint64_t da, uint64_t db, int sd = 0){
  if constexpr (ACC == 1) asm volatile("wgmma.mma_async.sync.aligned.m64n128k16.f32.bf16.bf16 {%0,%1,%2,%3,%4,%5,%6,%7,%8,%9,%10,%11,%12,%13,%14,%15,%16,%17,%18,%19,%20,%21,%22,%23,%24,%25,%26,%27,%28,%29,%30,%31,%32,%33,%34,%35,%36,%37,%38,%39,%40,%41,%42,%43,%44,%45,%46,%47,%48,%49,%50,%51,%52,%53,%54,%55,%56,%57,%58,%59,%60,%61,%62,%63}, %64, %65, 1, 1, 1, %67, %66;"
   : "+f"(d[O+0]), "+f"(d[O+1]), "+f"(d[O+2]), "+f"(d[O+3]), "+f"(d[O+4]), "+f"(d[O+5]), "+f"(d[O+6]), "+f"(d[O+7]), "+f"(d[O+8]), "+f"(d[O+9]), "+f"(d[O+10]), "+f"(d[O+11]), "+f"(d[O+12]), "+f"(d[O+13]), "+f"(d[O+14]), "+f"(d[O+15]), "+f"(d[O+16]), "+f"(d[O+17]), "+f"(d[O+18]), "+f"(d[O+19]), "+f"(d[O+20]), "+f"(d[O+21]), "+f"(d[O+22]), "+f"(d[O+23]), "+f"(d[O+24]), "+f"(d[O+25]), "+f"(d[O+26]), "+f"(d[O+27]), "+f"(d[O+28]), "+f"(d[O+29]), "+f"(d[O+30]), "+f"(d[O+31]), "+f"(d[O+32]), "+f"(d[O+33]), "+f"(d[O+34]), "+f"(d[O+35]), "+f"(d[O+36]), "+f"(d[O+37]), "+f"(d[O+38]), "+f"(d[O+39]), "+f"(d[O+40]), "+f"(d[O+41]), "+f"(d[O+42]), "+f"(d[O+43]), "+f"(d[O+44]), "+f"(d[O+45]), "+f"(d[O+46]), "+f"(d[O+47]), "+f"(d[O+48]), "+f"(d[O+49]), "+f"(d[O+50]), "+f"(d[O+51]), "+f"(d[O+52]), "+f"(d[O+53]), "+f"(d[O+54]), "+f"(d[O+55]), "+f"(d[O+56]), "+f"(d[O+57]), "+f"(d[O+58]), "+f"(d[O+59]), "+f"(d[O+60]), "+f"(d[O+61]), "+f"(d[O+62]), "+f"(d[O+63])
   : "l"(da), "l"(db), "n"(TB & 1), "n"(TB >> 1));
  else if constexpr (ACC == 0) asm volatile("wgmma.mma_async.sync.aligned.m64n128k16.f32.bf16.bf16 {%0,%1,%2,%3,%4,%5,%6,%7,%8,%9,%10,%11,%12,%13,%14,%15,%16,%17,%18,%19,%20,%21,%22,%23,%24,%25,%26,%27,%28,%29,%30,%31,%32,%33,%34,%35,%36,%37,%38,%39,%40,%41,%42,%43,%44,%45,%46,%47,%48,%49,%50,%51,%52,%53,%54,%55,%56,%57,%58,%59,%60,%61,%62,%63}, %64, %65, 0, 1, 1, %67, %66;"
   : "=f"(d[O+0]), "=f"(d[O+1]), "=f"(d[O+2]), "=f"(d[O+3]), "=f"(d[O+4]), "=f"(d[O+5]), "=f"(d[O+6]), "=f"(d[O+7]), "=f"(d[O+8]), "=f"(d[O+9]), "=f"(d[O+10]), "=f"(d[O+11]), "=f"(d[O+12]), "=f"(d[O+13]), "=f"(d[O+14]), "=f"(d[O+15]), "=f"(d[O+16]), "=f"(d[O+17]), "=f"(d[O+18]), "=f"(d[O+19]), "=f"(d[O+20]), "=f"(d[O+21]), "=f"(d[O+22]), "=f"(d[O+23]), "=f"(d[O+24]), "=f"(d[O+25]), "=f"(d[O+26]), "=f"(d[O+27]), "=f"(d[O+28]), "=f"(d[O+29]), "=f"(d[O+30]), "=f"(d[O+31]), "=f"(d[O+32]), "=f"(d[O+33]), "=f"(d[O+34]), "=f"(d[O+35]), "=f"(d[O+36]), "=f"(d[O+37]), "=f"(d[O+38]), "=f"(d[O+39]), "=f"(d[O+40]), "=f"(d[O+41]), "=f"(d[O+42]), "=f"(d[O+43]), "=f"(d[O+44]), "=f"(d[O+45]), "=f"(d[O+46]), "=f"(d[O+47]), "=f"(d[O+48]), "=f"(d[O+49]), "=f"(d[O+50]), "=f"(d[O+51]), "=f"(d[O+52]), "=f"(d[O+53]), "=f"(d[O+54]), "=f"(d[O+55]), "=f"(d[O+56]), "=f"(d[O+57]), "=f"(d[O+58]), "=f"(d[O+59]), "=f"(d[O+60]), "=f"(d[O+61]), "=f"(d[O+62]), "=f"(d[O+63])
   : "l"(da), "l"(db), "n"(TB & 1), "n"(TB >> 1));
  else asm volatile("{\n.reg .pred p;\nsetp.ne.b32 p, %68, 0;\nwgmma.mma_async.sync.aligned.m64n128k16.f32.bf16.bf16 {%0,%1,%2,%3,%4,%5,%6,%7,%8,%9,%10,%11,%12,%13,%14,%15,%16,%17,%18,%19,%20,%21,%22,%23,%24,%25,%26,%27,%28,%29,%30,%31,%32,%33,%34,%35,%36,%37,%38,%39,%40,%41,%42,%43,%44,%45,%46,%47,%48,%49,%50,%51,%52,%53,%54,%55,%56,%57,%58,%59,%60,%61,%62,%63}, %64, %65, p, 1, 1, %67, %66;\n}"
   : "+f"(d[O+0]), "+f"(d[O+1]), "+f"(d[O+2]), "+f"(d[O+3]), "+f"(d[O+4]), "+f"(d[O+5]), "+f"(d[O+6]), "+f"(d[O+7]), "+f"(d[O+8]), "+f"(d[O+9]), "+f"(d[O+10]), "+f"(d[O+11]), "+f"(d[O+12]), "+f"(d[O+13]), "+f"(d[O+14]), "+f"(d[O+15]), "+f"(d[O+16]), "+f"(d[O+17]), "+f"(d[O+18]), "+f"(d[O+19]), "+f"(d[O+20]), "+f"(d[O+21]), "+f"(d[O+22]), "+f"(d[O+23]), "+f"(d[O+24]), "+f"(d[O+25]), "+f"(d[O+26]), "+f"(d[O+27]), "+f"(d[O+28]), "+f"(d[O+29]), "+f"(d[O+30]), "+f"(d[O+31]), "+f"(d[O+32]), "+f"(d[O+33]), "+f"(d[O+34]), "+f"(d[O+35]), "+f"(d[O+36]), "+f"(d[O+37]), "+f"(d[O+38]), "+f"(d[O+39]), "+f"(d[O+40]), "+f"(d[O+41]), "+f"(d[O+42]), "+f"(d[O+43]), "+f"(d[O+44]), "+f"(d[O+45]), "+f"(d[O+46]), "+f"(d[O+47]), "+f"(d[O+48]), "+f"(d[O+49]), "+f"(d[O+50]), "+f"(d[O+51]), "+f"(d[O+52]), "+f"(d[O+53]), "+f"(d[O+54]), "+f"(d[O+55]), "+f"(d[O+56]), "+f"(d[O+57]), "+f"(d[O+58]), "+f"(d[O+59]), "+f"(d[O+60]), "+f"(d[O+61]), "+f"(d[O+62]), "+f"(d[O+63])
   : "l"(da), "l"(db), "n"(TB & 1), "n"(TB >> 1), "r"(sd));
}
template<int O,int TB,int ACC,int NN> __device__ __forceinline__ void mma_rs128(float (&d)[NN], uint32_t a0, uint32_t a1, uint32_t a2, uint32_t a3, uint64_t db, int sd = 0){
  if constexpr (ACC == 1) asm volatile("wgmma.mma_async.sync.aligned.m64n128k16.f32.bf16.bf16 {%0,%1,%2,%3,%4,%5,%6,%7,%8,%9,%10,%11,%12,%13,%14,%15,%16,%17,%18,%19,%20,%21,%22,%23,%24,%25,%26,%27,%28,%29,%30,%31,%32,%33,%34,%35,%36,%37,%38,%39,%40,%41,%42,%43,%44,%45,%46,%47,%48,%49,%50,%51,%52,%53,%54,%55,%56,%57,%58,%59,%60,%61,%62,%63}, {%64,%65,%66,%67}, %68, 1, 1, 1, %69;"
   : "+f"(d[O+0]), "+f"(d[O+1]), "+f"(d[O+2]), "+f"(d[O+3]), "+f"(d[O+4]), "+f"(d[O+5]), "+f"(d[O+6]), "+f"(d[O+7]), "+f"(d[O+8]), "+f"(d[O+9]), "+f"(d[O+10]), "+f"(d[O+11]), "+f"(d[O+12]), "+f"(d[O+13]), "+f"(d[O+14]), "+f"(d[O+15]), "+f"(d[O+16]), "+f"(d[O+17]), "+f"(d[O+18]), "+f"(d[O+19]), "+f"(d[O+20]), "+f"(d[O+21]), "+f"(d[O+22]), "+f"(d[O+23]), "+f"(d[O+24]), "+f"(d[O+25]), "+f"(d[O+26]), "+f"(d[O+27]), "+f"(d[O+28]), "+f"(d[O+29]), "+f"(d[O+30]), "+f"(d[O+31]), "+f"(d[O+32]), "+f"(d[O+33]), "+f"(d[O+34]), "+f"(d[O+35]), "+f"(d[O+36]), "+f"(d[O+37]), "+f"(d[O+38]), "+f"(d[O+39]), "+f"(d[O+40]), "+f"(d[O+41]), "+f"(d[O+42]), "+f"(d[O+43]), "+f"(d[O+44]), "+f"(d[O+45]), "+f"(d[O+46]), "+f"(d[O+47]), "+f"(d[O+48]), "+f"(d[O+49]), "+f"(d[O+50]), "+f"(d[O+51]), "+f"(d[O+52]), "+f"(d[O+53]), "+f"(d[O+54]), "+f"(d[O+55]), "+f"(d[O+56]), "+f"(d[O+57]), "+f"(d[O+58]), "+f"(d[O+59]), "+f"(d[O+60]), "+f"(d[O+61]), "+f"(d[O+62]), "+f"(d[O+63])
   : "r"(a0), "r"(a1), "r"(a2), "r"(a3), "l"(db), "n"(TB));
  else if constexpr (ACC == 0) asm volatile("wgmma.mma_async.sync.aligned.m64n128k16.f32.bf16.bf16 {%0,%1,%2,%3,%4,%5,%6,%7,%8,%9,%10,%11,%12,%13,%14,%15,%16,%17,%18,%19,%20,%21,%22,%23,%24,%25,%26,%27,%28,%29,%30,%31,%32,%33,%34,%35,%36,%37,%38,%39,%40,%41,%42,%43,%44,%45,%46,%47,%48,%49,%50,%51,%52,%53,%54,%55,%56,%57,%58,%59,%60,%61,%62,%63}, {%64,%65,%66,%67}, %68, 0, 1, 1, %69;"
   : "=f"(d[O+0]), "=f"(d[O+1]), "=f"(d[O+2]), "=f"(d[O+3]), "=f"(d[O+4]), "=f"(d[O+5]), "=f"(d[O+6]), "=f"(d[O+7]), "=f"(d[O+8]), "=f"(d[O+9]), "=f"(d[O+10]), "=f"(d[O+11]), "=f"(d[O+12]), "=f"(d[O+13]), "=f"(d[O+14]), "=f"(d[O+15]), "=f"(d[O+16]), "=f"(d[O+17]), "=f"(d[O+18]), "=f"(d[O+19]), "=f"(d[O+20]), "=f"(d[O+21]), "=f"(d[O+22]), "=f"(d[O+23]), "=f"(d[O+24]), "=f"(d[O+25]), "=f"(d[O+26]), "=f"(d[O+27]), "=f"(d[O+28]), "=f"(d[O+29]), "=f"(d[O+30]), "=f"(d[O+31]), "=f"(d[O+32]), "=f"(d[O+33]), "=f"(d[O+34]), "=f"(d[O+35]), "=f"(d[O+36]), "=f"(d[O+37]), "=f"(d[O+38]), "=f"(d[O+39]), "=f"(d[O+40]), "=f"(d[O+41]), "=f"(d[O+42]), "=f"(d[O+43]), "=f"(d[O+44]), "=f"(d[O+45]), "=f"(d[O+46]), "=f"(d[O+47]), "=f"(d[O+48]), "=f"(d[O+49]), "=f"(d[O+50]), "=f"(d[O+51]), "=f"(d[O+52]), "=f"(d[O+53]), "=f"(d[O+54]), "=f"(d[O+55]), "=f"(d[O+56]), "=f"(d[O+57]), "=f"(d[O+58]), "=f"(d[O+59]), "=f"(d[O+60]), "=f"(d[O+61]), "=f"(d[O+62]), "=f"(d[O+63])
   : "r"(a0), "r"(a1), "r"(a2), "r"(a3), "l"(db), "n"(TB));
  else asm volatile("{\n.reg .pred p;\nsetp.ne.b32 p, %70, 0;\nwgmma.mma_async.sync.aligned.m64n128k16.f32.bf16.bf16 {%0,%1,%2,%3,%4,%5,%6,%7,%8,%9,%10,%11,%12,%13,%14,%15,%16,%17,%18,%19,%20,%21,%22,%23,%24,%25,%26,%27,%28,%29,%30,%31,%32,%33,%34,%35,%36,%37,%38,%39,%40,%41,%42,%43,%44,%45,%46,%47,%48,%49,%50,%51,%52,%53,%54,%55,%56,%57,%58,%59,%60,%61,%62,%63}, {%64,%65,%66,%67}, %68, p, 1, 1, %69;\n}"
   : "+f"(d[O+0]), "+f"(d[O+1]), "+f"(d[O+2]), "+f"(d[O+3]), "+f"(d[O+4]), "+f"(d[O+5]), "+f"(d[O+6]), "+f"(d[O+7]), "+f"(d[O+8]), "+f"(d[O+9]), "+f"(d[O+10]), "+f"(d[O+11]), "+f"(d[O+12]), "+f"(d[O+13]), "+f"(d[O+14]), "+f"(d[O+15]), "+f"(d[O+16]), "+f"(d[O+17]), "+f"(d[O+18]), "+f"(d[O+19]), "+f"(d[O+20]), "+f"(d[O+21]), "+f"(d[O+22]), "+f"(d[O+23]), "+f"(d[O+24]), "+f"(d[O+25]), "+f"(d[O+26]), "+f"(d[O+27]), "+f"(d[O+28]), "+f"(d[O+29]), "+f"(d[O+30]), "+f"(d[O+31]), "+f"(d[O+32]), "+f"(d[O+33]), "+f"(d[O+34]), "+f"(d[O+35]), "+f"(d[O+36]), "+f"(d[O+37]), "+f"(d[O+38]), "+f"(d[O+39]), "+f"(d[O+40]), "+f"(d[O+41]), "+f"(d[O+42]), "+f"(d[O+43]), "+f"(d[O+44]), "+f"(d[O+45]), "+f"(d[O+46]), "+f"(d[O+47]), "+f"(d[O+48]), "+f"(d[O+49]), "+f"(d[O+50]), "+f"(d[O+51]), "+f"(d[O+52]), "+f"(d[O+53]), "+f"(d[O+54]), "+f"(d[O+55]), "+f"(d[O+56]), "+f"(d[O+57]), "+f"(d[O+58]), "+f"(d[O+59]), "+f"(d[O+60]), "+f"(d[O+61]), "+f"(d[O+62]), "+f"(d[O+63])
   : "r"(a0), "r"(a1), "r"(a2), "r"(a3), "l"(db), "n"(TB), "r"(sd));
}


constexpr int WB = 8;
constexpr int WSLEEP = 20;
constexpr int MSPLIT = 2;
constexpr int TH = 4;
constexpr int PF0 = 4;
constexpr int FSPLIT = 1;
constexpr int GKB = 4;
constexpr int T0A = 7;
constexpr int T0B = 11;
constexpr int OA = 3;
constexpr int OB = 11;
constexpr int EB = 8;
constexpr int SPACE = 100;
template <int V> struct IC { static constexpr int value = V; };
struct Maps { CUtensorMap x, ft, g64, u64, e, wr, wi, xs, ts, t, g32, u32, d224, fg; };

constexpr int NCTA = 130;
constexpr int U = 16384;
constexpr int TB = 36864;
constexpr int OFF_RING = 8 * U, OFF_Z = 12 * U, OFF_XB = 12 * U, OFF_T = 13 * U, OFF_D = OFF_T;
constexpr int OFF_BAR = 14 * U, OFF_SP = OFF_BAR + 512, OFF_G = OFF_SP + 1024 + 128;
constexpr int SMEM_BYTES = OFF_G + 512;
constexpr int B_FX = 0, B_FA = 8, B_FT = 12, B_Z = 16, B_W = 24, B_HX = 25, B_TL = 26, B_HP = 27, B_WR = 31;
constexpr int B_EA = 36, B_ET = 40, B_PZ = 44, B_RDY = 46, B_FE = 47;
constexpr int B_T = 51, B_XS = 52, B_G = 54, B_RD0 = 55, NBAR = 56;
__device__ __forceinline__ int srow(int rb, int r) { return 2 * rb + (r >> 6) + 32 * (r & 7) + 256 * ((r >> 4) & 3) + 1024 * ((r >> 3) & 1); }
__host__ __device__ constexpr int rslot(int n) { return n & 3; }
__host__ __device__ constexpr int rpar(int n) { return (n >> 2) & 1; }

__global__ void __cluster_dims__(2, 1, 1) __launch_bounds__(512, 1)
fused_kernel(Work* __restrict__ ws, const uint16_t* __restrict__ dtab, const __nv_bfloat16* __restrict__ w_r, const __nv_bfloat16* __restrict__ w_i,
             const __nv_bfloat16* __restrict__ gate_w, const __nv_bfloat16* __restrict__ x, __nv_bfloat16* __restrict__ out,
             const __grid_constant__ Maps maps) {
  extern __shared__ __align__(1024) uint8_t smem[];
  if (threadIdx.x < 32 && elect_one()) {
#pragma unroll
    for (int i = 0; i < PF0; i++) asm volatile("prefetch.tensormap [%0];" ::"l"((const char*)&maps + i * 128) : "memory");
  }
  const uint32_t sb = smem_u32(smem);
  const uint32_t bars = sb + OFF_BAR;
  const int tid = threadIdx.x, lane = tid & 31;
  const int warp = __shfl_sync(0xffffffffu, tid >> 5, 0);
  const bool helper = blockIdx.x >= 128;
  const int cl = (blockIdx.x >> 1) & 63, rank = blockIdx.x & 1;
  const int q4 = (cl & 1) | ((cl >> 2) & 2), rb = ((cl >> 1) & 3) | ((cl >> 4) << 2);
  const int j = 2 * q4 + rank;
  const int f_full = 448 * q4 + (rank ? 256 : 0);
  const int f_half = 448 * q4 + (rank ? 224 : 192);
  if (warp < 8) {
    if (!helper && tid < 32) {
      const int r = 16 * j + (tid & 15);
      asm volatile("prefetch.global.L2 [%0];" ::"l"(x + (size_t)srow(rb, r) * 512 + 64 * (tid >> 4)));
    }
    asm volatile("barrier.cluster.arrive.relaxed.aligned;" ::: "memory");
    asm volatile("setmaxnreg.inc.sync.aligned.u32 192;");
    if (!helper) {
      const int wg = warp >> 2, w = warp & 3, g = lane >> 2;
      const bool elect = (tid & 127) == 0;
      float cX[32], cD[64], cA[64], cB[64], cC[64], ci[64], ct[64];
      const int zero = blockIdx.x >> 16;
      uint32_t h[56], yf[16];
      const uint32_t d0 = (sb & 0x3FFFF) >> 4;
      const uint32_t dK = d0 | (1u << 16), dN = d0 | (512u << 16);
      const uint32_t dX = dK + wg * 512;
      constexpr uint32_t RING = OFF_RING >> 4;
      auto waitA = [&](int n) { mbar_wait(bars + 8 * (B_FA + rslot(n)), rpar(n)); };
      auto freeA = [&](int n) { mbar_arrive_if(elect, bars + 8 * (B_EA + rslot(n))); };
      auto nop = [] {};

      asm volatile("bar.sync 0, 384;" ::: "memory");
#pragma unroll 1
      for (int i = 0; i < 4; i++) {
        const uint64_t dx = d128(dX + i * 2048), df = d128(dK + (OFF_XB >> 4) + (i & 1) * 1024);
        mbar_wait(bars + 8 * (B_FX + 2 * i), 0);
        wg_fence();
        mma_ss64<0, 0, 2>(cX, df, dx, i);
        mma_ss64<0, 0, 1>(cX, df + 2, dx + 2);
        wg_commit(); wg_wait<1>();
        mbar_arrive_if(elect && i, bars + 8 * (B_EA + rslot(i - 1)));
        mma_ss64<0, 0, 1>(cX, df + 4, dx + 4);
        mma_ss64<0, 0, 1>(cX, df + 6, dx + 6);
        mbar_wait(bars + 8 * (B_FX + 2 * i + 1), 0);
        wg_fence();
#pragma unroll
        for (int k = 0; k < 4; k++) mma_ss64<0, 0, 1>(cX, df + (512 + k * 2), dx + (1024 + k * 2));
        wg_commit();
        waitA(i);
        wg_fence();
        const uint64_t da = d128(dX + i * 1024), db = d128(dN + RING + i * 1024);
        mma_ss128<0, 1, 2>(cA, da, db, i);
        wg_commit(); wg_wait<1>();
        mbar_arrive_if(elect, bars + 8 * (B_FE + i));
#pragma unroll
        for (int k = 1; k < 4; k++) mma_ss128<0, 1, 1>(cA, da + k * 2, db + k * 128);
        wg_commit();
      }
      fence_regs<0, 32>(cX);
#pragma unroll
      for (int e = 0; e < 8; e++) {
        const int o = 8 * (e >> 1) + 2 * (e & 1);
        yf[e] = pack_pin(cX[o] + cX[o + 4], cX[o + 1] + cX[o + 5]); yf[8 + e] = pack_pin(cX[o] - cX[o + 4], cX[o + 1] - cX[o + 5]);
      }
      {
        waitA(4);
        const uint64_t de = d128(dN + RING + wg * 512);
        wg_fence();
        mma_rs64<0, 1, 0>(cD, yf[0], yf[1], yf[2], yf[3], de);
        mma_rs64<32, 1, 0>(cD, yf[8], yf[9], yf[10], yf[11], de + 256);
        wg_commit();
        wg_wait<1>();
        freeA(3);
        mma_rs64<0, 1, 1>(cD, yf[4], yf[5], yf[6], yf[7], de + 128);
        mma_rs64<32, 1, 1>(cD, yf[12], yf[13], yf[14], yf[15], de + 384);
        wg_commit();
      }
      bool rel = false;
      auto acquire = [&](int n) {
        rel = elect;
        if (!mbar_try(bars + 8 * (B_FA + rslot(n)), rpar(n))) { wg_wait<0>(); freeA(n - 1); rel = false; waitA(n); }
      };
      auto freeP = [&](int n) { mbar_arrive_if(rel, bars + 8 * (B_EA + rslot(n - 1))); };
      auto ffn_step = [&](auto first, auto split, float (&acc)[64], int n, int kb, auto done, auto work) {
        constexpr int SPLIT = decltype(split)::value;
        acquire(n);
        wg_fence();
        const uint64_t dx = d128(dX + kb * 1024), db = d128(dN + RING + rslot(n) * 1024);
        mma_ss128<0, 1, decltype(first)::value>(acc, dx, db, kb);
#pragma unroll
        for (int k = 1; k < SPLIT; k++) mma_ss128<0, 1, 1>(acc, dx + k * 2, db + k * 128);
        wg_commit();
        work();
        wg_wait<1>();
        freeP(n);
        done();
        if (SPLIT < 4) {
          wg_fence();
#pragma unroll
          for (int k = SPLIT; k < 4; k++) mma_ss128<0, 1, 1>(acc, dx + k * 2, db + k * 128);
          wg_commit();
        }
      };
      {
        const int s0 = 2 * rb + wg, kr = 2 * ((s0 & 1) | ((s0 & 4) >> 1));
        const int m = lane >> 3, r = lane & 7;
        const uint32_t a0 = sb + OFF_XB + wg * 8192 + ((2 * (m >> 1) + (r >> 2)) * 2 + (w & 1)) * 256 + (m & 1) * 128 + (((2 * (r & 3) + ((w >> 1) ^ (r >> 2))) ^ (kr + (m & 1))) << 4);
        ffn_step(IC<1>(), IC<4>(), cA, 5, 4, [&] { fence_regs<0, 64>(cD); }, [&] { mbar_wait(bars + 8 * (B_FE + 2), 0); });
        auto stage = [&](int i) {
          const int o = 32 * (i >> 1) + 8 * (i & 1);
          stsm4t(a0 + i * 2048, pack_bf16(cD[o] - cD[o + 18], cD[o + 1] - cD[o + 19]), pack_bf16(cD[o + 16] + cD[o + 2], cD[o + 17] + cD[o + 3]),
                 pack_bf16(cD[o + 4] - cD[o + 22], cD[o + 5] - cD[o + 23]), pack_bf16(cD[o + 20] + cD[o + 6], cD[o + 21] + cD[o + 7]));
          if (j == 0 && w == 0) {
            const uint32_t a1 = r ? sb + OFF_SP + 1024 : sb + OFF_SP + wg * 512 + (m & 1) * 256 + (m >> 1) * 128;
#pragma unroll
            for (int n = 0; n < 2; n++)
              asm volatile("stmatrix.sync.aligned.m8n8.x4.shared.b16 [%0], {%1,%2,%3,%4};" ::"r"(a1 + (((2 * i + n) ^ (kr + (m >> 1)) ^ r) << 4)),
                           "r"(pack_bf16(cD[o + 4 * n], cD[o + 4 * n + 1])), "r"(pack_bf16(cD[o + 4 * n + 2], cD[o + 4 * n + 3])),
                           "r"(pack_bf16(cD[o + 16 + 4 * n], cD[o + 17 + 4 * n])), "r"(pack_bf16(cD[o + 18 + 4 * n], cD[o + 19 + 4 * n])) : "memory");
          }
        };
        auto publish = [&] {
          asm volatile("fence.proxy.async.shared::cta;" ::: "memory");
          __syncwarp();
          mbar_arrive_if(lane == 0, bars + 8 * (B_XS + wg));
        };
        stage(0);
        ffn_step(IC<1>(), IC<FSPLIT>(), cA, 6, 5, nop, nop);
        stage(1);
        ffn_step(IC<1>(), IC<FSPLIT>(), cA, 7, 6, nop, nop);
        stage(2);
        ffn_step(IC<1>(), IC<2>(), cA, 8, 7, [&] { stage(3); }, nop);
        publish();
      }
      uint32_t gb0 = 0, gb1 = 0;
      uint32_t ob[2] = {0, 0};
      auto glu = [&](auto& acc, int half, int ho, int i0, int i1) {
#pragma unroll
        for (int i = i0; i < i1; i++)
          asm volatile("{\n.reg .b32 a, b;\ncvt.rn.relu.bf16x2.f32 a, %2, %1;\ncvt.rn.bf16x2.f32 b, %4, %3;\nmul.rn.bf16x2 a, a, b;\nmul.rn.bf16x2 %0, a, %5;\n}"
                       : "=r"(h[ho + i]) : "f"(acc[2 * i]), "f"(acc[2 * i + 1]), "f"(acc[half + 2 * i]), "f"(acc[half + 1 + 2 * i]), "r"(ob[i & 1]) : "memory");
      };
      ffn_step(IC<0>(), IC<1>(), cB, 9, 0, nop, nop);
#pragma unroll 1
      for (int kb = 1; kb < 8; kb++)
        ffn_step(IC<1>(), IC<FSPLIT>(), cB, 9 + kb, kb, nop, [&] {
          if (kb == GKB) {
            mbar_wait(bars + 8 * B_G, 0);
            asm volatile("ld.shared.u32 %0, [%2];\nld.shared.u32 %1, [%2+32];" : "=r"(gb0), "=r"(gb1) : "r"(sb + OFF_G + (wg * 64 + w * 16 + g) * 4) : "memory");
          } else if (kb == 5 + 2 * wg) {
            ob[0] = pack_bf16(1.0f - bf_hi(gb0), 1.0f - bf_hi(gb0)); ob[1] = pack_bf16(1.0f - bf_hi(gb1), 1.0f - bf_hi(gb1));
            glu(cA, 32, 0, 0, 16);
          }
        });
      const uint32_t tag = gb0 & 1;
      const float g0 = bf_hi(gb0), g1 = bf_hi(gb1);
      auto m_step = [&](auto first, int i) {
        acquire(17 + i);
        wg_fence();
        const uint64_t dx = d128(dX + i * 2048), dm = d64(dN + RING + rslot(17 + i) * 1024);
        mma_ss64<0, 1, decltype(first)::value>(ct, dx, dm);
#pragma unroll
        for (int k = 1; k < MSPLIT; k++) mma_ss64<0, 1, 1>(ct, dx + ((k >> 2) * 1024 + (k & 3) * 2), dm + k * 64);
        wg_commit();
        wg_wait<1>();
        freeP(17 + i);
        wg_fence();
#pragma unroll
        for (int k = MSPLIT; k < 8; k++) mma_ss64<0, 1, 1>(ct, dx + ((k >> 2) * 1024 + (k & 3) * 2), dm + k * 64);
        wg_commit();
      };
      m_step(IC<0>(), 0);
#pragma unroll 1
      for (int i = 1; i < 5; i++) {
        if (i == 1 + 2 * wg) glu(cB, 32, 16, 0, 16);
        if (i < 4) m_step(IC<1>(), i);
      }
      ffn_step(IC<0>(), IC<1>(), cC, 21, 0, nop, nop);
#pragma unroll 1
      for (int kb = 1; kb < 8; kb++)
        ffn_step(IC<1>(), IC<FSPLIT>(), cC, 21 + kb, kb, [&] { mbar_arrive_if(elect && !(kb & 1), bars + 8 * (B_ET + (kb >> 1) - 1)); }, [&] {
          if (kb == 1 + wg) glu(ct, 16, 48, 0, 8);
        });

      const int fo = warp * 128 + lane;
      auto fetch = [&](uint4 (&pv)[4], int z) {
        mbar_wait(bars + 8 * (z < 4 ? B_Z + 2 * z + wg : z < 6 ? B_HP + z - 4 : B_HP + 2 + wg), 0);
        const uint8_t* src = smem + (z < 4 ? OFF_Z - z * U : z == 4 ? OFF_T : (z - 5) * U) + fo * 16;
#pragma unroll
        for (int i = 0; i < 4; i++) pv[i] = *(const uint4*)(src + i * 512);
      };
      const uint32_t peerZ = mapa(sb + OFF_Z + fo * 16, rank ^ 1), peerB = mapa(bars + 8 * (B_Z + wg), rank ^ 1);
      auto tile_mma = [&](auto off, int t, int k0, int k1, bool fresh = false) {
        constexpr int O = decltype(off)::value;
        const uint64_t db = d128(dN + (t & 3) * (TB >> 4)), dw = db + rank * 256, dm = db + (rank ? 0 : 1536);
#pragma unroll
        for (int k = k0; k < k1; k++) {
          if (k == 0 && O == 0) mma_rs64<O, 1, 2>(ct, h[0], h[1], h[2], h[3], dw, zero);
          else if (k < 14) mma_rs64<O, 1, 1>(ct, h[4 * k], h[4 * k + 1], h[4 * k + 2], h[4 * k + 3], k < 12 ? dw + k * 128 : dm + (k - 12) * 128);
          else if (k == 14 && fresh) mma_rs64<O, 1, 0>(ct, yf[0], yf[1], yf[2], yf[3], db + k * 128);
          else if (k == 14) mma_rs64<O, 1, 2>(ct, yf[0], yf[1], yf[2], yf[3], db + k * 128, zero);
          else mma_rs64<O, 1, 1>(ct, yf[4 * k - 56], yf[4 * k - 55], yf[4 * k - 54], yf[4 * k - 53], db + k * 128);
        }
      };
      uint4 pv[4];
      const uint32_t sgn = rank ? 0x80008000u : 0u;
      auto even_end = [&](int t, int k0, bool fresh) {
        wg_fence();
        tile_mma(IC<32>(), t, 14, 18, fresh);
        wg_commit();
        tile_mma(IC<0>(), t, k0, 14);
        wg_commit();
        wg_wait<1>();
        fence_regs<32, 32>(ct);
#pragma unroll
        for (int i = 0; i < 4; i++)
          pv[i] = make_uint4(pack_pin(ct[32 + 8 * i], ct[33 + 8 * i]) ^ sgn, pack_pin(ct[34 + 8 * i], ct[35 + 8 * i]) ^ sgn,
                             pack_pin(ct[36 + 8 * i], ct[37 + 8 * i]) ^ sgn, pack_pin(ct[38 + 8 * i], ct[39 + 8 * i]) ^ sgn);
      };
      auto odd_head = [&](int t) {
        mbar_wait(bars + 8 * (B_FT + (t & 3)), t >> 2);
        wg_fence();
        tile_mma(IC<32>(), t, 0, OA);
        wg_commit();
        if (t < 4) mbar_wait(bars + 8 * (t == 1 ? B_RD0 : B_RDY), 0);
        wg_wait<1>();
        mbar_arrive_if(elect && t < 6, bars + 8 * (B_ET + t - 1));
        fence_regs<0, 32>(ct);
        wg_fence();
#pragma unroll
        for (int i = 0; i < 4; i++) {
          asm volatile("st.async.weak.shared::cluster.mbarrier::complete_tx::bytes.v4.b32 [%0], {%2,%3,%4,%5}, [%1];" ::"r"(peerZ - (t >> 1) * U + i * 512),
                       "r"(peerB + 16 * (t >> 1)), "r"(add_bf2(pv[i].x, pack_bf16(ct[8 * i], ct[8 * i + 1]))), "r"(add_bf2(pv[i].y, pack_bf16(ct[8 * i + 2], ct[8 * i + 3]))),
                       "r"(add_bf2(pv[i].z, pack_bf16(ct[8 * i + 4], ct[8 * i + 5]))), "r"(add_bf2(pv[i].w, pack_bf16(ct[8 * i + 6], ct[8 * i + 7]))) : "memory");
          tile_mma(IC<32>(), t, OA + i, OA + i + 1);
        }
        wg_commit();
      };
      asm volatile("barrier.cluster.wait.aligned;" ::: "memory");
      mbar_wait(bars + 8 * B_FT, 0);
      wg_fence();
      tile_mma(IC<0>(), 0, 0, T0A);
      wg_commit();
      waitA(29);
      wg_wait<1>();
      mbar_arrive_if(elect, bars + 8 * (B_ET + 3));
      glu(cC, 32, 32, 0, 16);
      mbar_wait(bars + 8 * (j == 0 ? B_T : B_TL), 0);
      wg_fence();
      {
        const uint64_t dt = d128(dN + (OFF_T >> 4) + wg * 512), de = d128(dK + RING + 1024 + wg * 512);
        mma_ss64<0, 1, 0>(ci, de, dt);
        mma_ss64<32, 1, 0>(ci, de + 4, dt + 256);
        mma_ss64<0, 1, 1>(ci, de + 2, dt + 128);
        mma_ss64<32, 1, 1>(ci, de + 6, dt + 384);
        wg_commit();
      }
      tile_mma(IC<0>(), 0, T0A, T0B);
      wg_commit();
      wg_wait<1>();
      if (elect) asm volatile("mbarrier.arrive.shared::cluster.b64 _, [%0];" ::"r"(mapa(bars + 8 * B_RDY, rank ^ 1)) : "memory");
      mbar_arrive_if(elect, bars + 8 * (B_PZ + 1));
      fence_regs<0, 64>(ci);
#pragma unroll
      for (int n = 0; n < 8; n++) {
        const float s0 = g0 * (2.0f / (2048.0f * 512.0f)), s1 = g1 * (2.0f / (2048.0f * 512.0f));
        float u[4];
#pragma unroll
        for (int e = 0; e < 4; e++) {
          const int o = 32 * (e >> 1) + 4 * n + (e & 1);
          u[e] = (n & 1) ? ci[o] - ci[o - 2] : ci[o] + ci[o + 6];
        }
        yf[2 * n] = pack_pin((u[0] + u[2]) * s0, (u[1] + u[3]) * s0); yf[2 * n + 1] = pack_pin((u[0] - u[2]) * s1, (u[1] - u[3]) * s1);
      }
      even_end(0, T0B, true);
#pragma unroll 1
      for (int t = 1; t < 7; t += 2) {
        odd_head(t);
        wg_fence();
        tile_mma(IC<32>(), t, OA + 4, 14);
        wg_commit();
        const int zo = t >> 1, owner = rb * 8 + 2 * ((q4 + zo + 1) & 3) + rank;
        uint4* dst = ws->part + (size_t)(owner * 3 + zo) * 1024 + fo;
        auto send = [&] {
          fence_regs<32, 32>(ct);
#pragma unroll
          for (int i = 0; i < 4; i++)
            asm volatile("st.relaxed.gpu.global.v4.u32 [%0], {%1,%2,%3,%4};" ::"l"(dst + i * 32),
                         "r"((add_bf2(pv[i].x, pack_bf16(ct[32 + 8 * i], ct[33 + 8 * i])) & ~1u) | tag), "r"(add_bf2(pv[i].y, pack_bf16(ct[34 + 8 * i], ct[35 + 8 * i]))),
                         "r"(add_bf2(pv[i].z, pack_bf16(ct[36 + 8 * i], ct[37 + 8 * i]))), "r"(add_bf2(pv[i].w, pack_bf16(ct[38 + 8 * i], ct[39 + 8 * i]))) : "memory");
          hint_add_if(lane == 0, &ws->cntP[32 * owner + 8 * (zo + (zo == 2 ? wg : 0))]);
        };
        if (t == 5) fetch(pv, 2);
        mbar_wait(bars + 8 * (B_FT + ((t + 1) & 3)), (t + 1) >> 2);
        wg_fence();
        tile_mma(IC<0>(), t + 1, 0, TH);
        wg_commit();
        wg_wait<1>();
        mbar_arrive_if(elect && t < 5, bars + 8 * (B_ET + t));
        if (t == 5) send(); else fetch(pv, zo);
        wg_fence();
        tile_mma(IC<0>(), t + 1, TH, EB);
        wg_commit();
        if (t != 5) send();
        even_end(t + 1, EB, false);
      }
      {
        uint4 p1[4], p2[4];
        auto acc4 = [&](uint4 (&d)[4], const uint4 (&a)[4]) {
#pragma unroll
          for (int i = 0; i < 4; i++) { d[i].x = add_bf2(d[i].x, a[i].x); d[i].y = add_bf2(d[i].y, a[i].y); d[i].z = add_bf2(d[i].z, a[i].z); d[i].w = add_bf2(d[i].w, a[i].w); }
        };
        auto add32 = [&](const uint4 (&a)[4]) {
#pragma unroll
          for (int i = 0; i < 4; i++) {
            const uint32_t u[4] = {a[i].x, a[i].y, a[i].z, a[i].w};
#pragma unroll
            for (int e = 0; e < 4; e++) { ct[32 + 8 * i + 2 * e] += bf_lo(u[e]); ct[33 + 8 * i + 2 * e] += bf_hi(u[e]); }
          }
        };
        odd_head(7);
        fetch(pv, 4);
        fetch(p1, 5);
        wg_fence();
        tile_mma(IC<32>(), 7, OA + 4, OB);
        wg_commit();
        uint32_t bad = 0;
#pragma unroll
        for (int i = 0; i < 4; i++) { bad |= (pv[i].x ^ tag) | (p1[i].x ^ tag); pv[i].x &= ~1u; p1[i].x &= ~1u; }
        acc4(pv, p1);
        fetch(p1, 3);
        wg_fence();
        tile_mma(IC<32>(), 7, OB, 14);
        wg_commit();
        fetch(p2, 6);
        wg_wait<0>();
        fence_regs<32, 32>(ct);
#pragma unroll
        for (int i = 0; i < 4; i++) bad |= p2[i].x ^ tag;
        if (__any_sync(0xffffffffu, bad & 1)) {
          const uint4* src = ws->part + (size_t)(rb * 8 + j) * 3 * 1024 + fo;
          uint4 p0[4];
          int n = 0;
          do {
            bad = 0;
#pragma unroll
            for (int i = 0; i < 4; i++) {
              pv[i] = ld_x4(src + i * 32); p0[i] = ld_x4(src + 1024 + i * 32); p2[i] = ld_x4(src + 2048 + i * 32);
              bad |= (pv[i].x ^ tag) | (p0[i].x ^ tag) | (p2[i].x ^ tag);
            }
            if (++n > (1 << 21)) __trap();
          } while (__any_sync(0xffffffffu, bad & 1));
#pragma unroll
          for (int i = 0; i < 4; i++) { pv[i].x &= ~1u; p0[i].x &= ~1u; }
          acc4(pv, p0);
        }
#pragma unroll
        for (int i = 0; i < 4; i++) p2[i].x &= ~1u;
        acc4(p1, p2);
        add32(pv); add32(p1);
#pragma unroll
        for (int i = 0; i < 4; i++)
          pv[i] = make_uint4(pack_bf16(ct[32 + 8 * i], ct[33 + 8 * i]), pack_bf16(ct[34 + 8 * i], ct[35 + 8 * i]), pack_bf16(ct[36 + 8 * i], ct[37 + 8 * i]), pack_bf16(ct[38 + 8 * i], ct[39 + 8 * i]));
        const uint32_t stg = sb + OFF_T + warp * 2048;
        const int mr = (lane & 7) + ((lane >> 3) & 1) * 8, mc = lane >> 4;
#pragma unroll
        for (int i = 0; i < 4; i++)
          asm volatile("stmatrix.sync.aligned.m8n8.x4.shared.b16 [%0], {%1,%2,%3,%4};" ::"r"(stg + mr * 128 + (((2 * i + mc) ^ (mr & 7)) << 4)), "r"(pv[i].x),
                       "r"(pv[i].y), "r"(pv[i].z), "r"(pv[i].w) : "memory");
        __syncwarp();
#pragma unroll
        for (int i = 0; i < 4; i++) {
          const int r = 4 * i + (lane >> 3), c = lane & 7;
          const uint4 v = *(const uint4*)(smem + OFF_T + warp * 2048 + r * 128 + ((c ^ (r & 7)) << 4));
          *(uint4*)(out + (size_t)srow(rb, 16 * warp + r) * 512 + 64 * (q4 + 4 * rank) + 8 * c) = v;
        }
      }
    }
  } else if (warp < 12) {
    asm volatile("setmaxnreg.dec.sync.aligned.u32 104;");
    asm volatile("barrier.cluster.arrive.relaxed.aligned;" ::: "memory");
    const int t = tid - 256, w = warp - 8;
    const uint32_t ep = ld_x1(&ws->epoch[blockIdx.x * 8]);
    const uint32_t tag = (ep + 1) & 1;
    auto w_issue = [&](const CUtensorMap* m) {
      if (elect_one()) { mbar_expect_tx(bars + 8 * (B_WR + w), 3072); tma4d(sb + OFF_T + w * 3072, m, bars + 8 * (B_WR + w), 32 * j, 0, 2 * w + (rb >> 3), rb & 7); }
      __syncwarp();
    };
    auto gate_rows = [&] {
      const int r = 16 * j + 4 * w + (lane >> 3);
      const uint4* pg = (const uint4*)gate_w + (lane & 7);
      {
        float a = 0.f;
        asm volatile("bar.sync 4, 256;" ::: "memory");
#pragma unroll 1
        for (int hf = 0; hf < 2; hf++) {
          uint4 v[4], u[4];
#pragma unroll
          for (int kb = 0; kb < 4; kb++) v[kb] = __ldg(pg + (4 * hf + kb) * 8);
          mbar_wait(bars + 8 * (B_FE + 1 + 2 * hf), 0);
          if (hf) w_issue(&maps.wr);
#pragma unroll
          for (int kb = 0; kb < 4; kb++) u[kb] = *(const uint4*)(smem + (4 * hf + kb) * U + r * 128 + (((lane ^ r) & 7) << 4));
#pragma unroll
          for (int kb = 0; kb < 4; kb++) {
            const uint32_t uu[4] = {u[kb].x, u[kb].y, u[kb].z, u[kb].w}, vv[4] = {v[kb].x, v[kb].y, v[kb].z, v[kb].w};
#pragma unroll
            for (int e = 0; e < 4; e++) {
              uint32_t pr;
              asm("mul.rn.bf16x2 %0, %1, %2;" : "=r"(pr) : "r"(uu[e]), "r"(vv[e]));
              a += bf_lo(pr) + bf_hi(pr);
            }
          }
        }
#pragma unroll
        for (int o = 4; o; o >>= 1) a += __shfl_xor_sync(0xffffffffu, a, o);
        if ((lane & 7) == 0)
          asm volatile("st.relaxed.gpu.global.u32 [%0], %1;" ::"l"(ws->gate + rb * 128 + r),
                       "r"(pack_bf16(0.f, __fdividef(1.0f, 1.0f + __expf(-bf_lo(pack_bf16(a, 0.f))))) | tag) : "memory");
      }
    };
    {
      const int g = lane >> 2, q = lane & 3;
      uint32_t wf[32];
      if (!helper) {
        gate_rows();
        const uint32_t wa = sb + OFF_T + w * (3072 + 4) + (rb >> 3) * 2 + q * 96 + g * 4, wb[2] = {wa + (rb & 1) * 32, wa + 32 - (rb & 1) * 32};
#pragma unroll 1
        for (int ri = 0; ri < 2; ri++) {
          mbar_wait(bars + 8 * (B_WR + w), ri);
#pragma unroll
          for (int n2 = 0; n2 < 32 / WB; n2++) {
            uint32_t v[WB];
#pragma unroll
            for (int i = 0; i < WB; i++) {
              const int e = n2 * WB + i;
              asm volatile("ld.shared.u16 %0, [%1];" : "=r"(v[i]) : "r"(wb[e & 1] + ((e >> 1) & 7) * 384 + (e >> 4) * 2) : "memory");
            }
#pragma unroll
            for (int i = 0; i < WB; i++) wf[n2 * WB + i] = __byte_perm(wf[n2 * WB + i], v[i], 0x5432);
            if (WSLEEP) { asm volatile("nanosleep.u32 %0;" ::"r"(WSLEEP + (v[WB - 1] >> 16)) : "memory"); }
          }
          __syncwarp();
          if (ri == 0) w_issue(&maps.wi);
        }
        asm volatile("bar.sync 1, 128;" ::: "memory");
      } else {
        asm volatile("bar.sync 4, 256;" ::: "memory");
        hint_wait(&ws->cntW[0], (ep + 1) * 128u);
        const uint32_t t0 = (uint32_t)clock();
#pragma unroll 1
        for (;;) {
          uint32_t bad = 0;
#pragma unroll
          for (int i = 0; i < 32; i++) {
            const float2 v = ld_x2((const float2*)ws->Wh + (i >> 4) * 2048 + 32 * (w & 1) + (w >> 1) + 2 * g + 16 * (i & 1) + 64 * q + ((i >> 1) & 7) * 256);
            wf[i] = __float_as_uint(v.x); bad |= __float_as_uint(v.y) ^ tag;
          }
          if (!__any_sync(0xffffffffu, bad & 1)) break;
          spin_guard(t0);
        }
      }
      if (w == 0 && elect_one()) { mbar_expect_tx(bars + 8 * B_W, 8192); bulk_load(sb + OFF_D, dtab, 8192, bars + 8 * B_W); }
      asm volatile("barrier.cluster.wait.aligned;" ::: "memory");
      mbar_wait(bars + 8 * B_W, 0);
      mbar_wait(bars + 8 * B_HX, 0);
      const uint32_t dd = (sb & 0x3FFFF) >> 4;
      const uint64_t dF = d128((dd + (OFF_D >> 4)) | (512u << 16)), dI = d128((dd + (OFF_D >> 4)) | (1u << 16)), dA = d128((dd + (OFF_XB >> 4)) | (512u << 16));
      float az[32];
      const int zero = blockIdx.x >> 16;
      uint32_t pf[32];
#pragma unroll
      for (int mt = 0; mt < 2; mt++) {
        wg_fence();
        if (mt == 0) mma_ss64<0, 3, 0>(az, dA, dF);
        else mma_ss64<0, 3, 2>(az, dA + 512, dF, zero);
#pragma unroll
        for (int k = 1; k < 4; k++) mma_ss64<0, 3, 1>(az, dA + (mt * 512 + k * 128), dF + k * 128);
        wg_commit();
        wg_wait<0>();
        fence_regs<0, 32>(az);
#pragma unroll
        for (int i = 0; i < 16; i++) {
          const float wr = bf_lo(wf[16 * mt + i]), wi = bf_hi(wf[16 * mt + i]);
          pf[16 * mt + i] = pack_pin(fmaf(az[2 * i], wr, -az[2 * i + 1] * wi), fmaf(az[2 * i], wi, az[2 * i + 1] * wr));
        }
      }
      {
        const int m = lane >> 3, r = lane & 7;
        const int sl = 2 * (m >> 1) + ((r >> 1) & 1) + 4 * (r >> 2);
        const uint32_t a0 = sb + OFF_XB + w * 4096 + sl * 64 + (((((m ^ rb) & 1) * 2 + (r & 1)) ^ (sl >> 1)) << 4);
        uint32_t pk[16];
#pragma unroll
        for (int mt = 0; mt < 3; mt++) {
          if (mt < 2) {
            wg_fence();
            mma_rs64<0, 0, 2>(az, pf[16 * mt], pf[16 * mt + 1], pf[16 * mt + 2], pf[16 * mt + 3], dI, mt ? (int)helper : zero);
#pragma unroll
            for (int k = 1; k < 4; k++) mma_rs64<0, 0, 1>(az, pf[16 * mt + 4 * k], pf[16 * mt + 4 * k + 1], pf[16 * mt + 4 * k + 2], pf[16 * mt + 4 * k + 3], dI + k * 2);
            wg_commit();
          }
          if (mt > 0 && !helper) {
#pragma unroll
            for (int i = 0; i < 4; i++) stsm4t(a0 + (mt - 1) * 2048 + i * 512, pk[4 * i], pk[4 * i + 1], pk[4 * i + 2], pk[4 * i + 3]);
          }
          if (mt < 2) {
            wg_wait<0>();
            fence_regs<0, 32>(az);
#pragma unroll
            for (int i = 0; i < 16; i++) pk[i] = pack_pin(az[2 * i], az[2 * i + 1]);
          }
        }
      }
      if (helper) {
#pragma unroll
        for (int i = 0; i < 16; i++) {
          const int n = i >> 1, s0 = 8 * (n >> 1) + 2 * (n & 1) + (q & 1) + 4 * (q >> 1);
          if ((n & 1) == (int)(blockIdx.x & 1)) st_u2(ws->Ts + s0 * 64 + 16 * w + g + 8 * (i & 1), pack_bf16(az[2 * i], az[2 * i + 1]), tag);
        }
        __syncwarp();
        hint_add_if(lane == 0, &ws->cntH[0]);
        if (t == 0) { ws->epoch[blockIdx.x * 8] = ep + 1; }
      } else {
        asm volatile("fence.proxy.async.shared::cta;" ::: "memory");
        __syncwarp();
        if (elect_one()) {
          if (SPACE) __nanosleep(SPACE * w);
          asm volatile("cp.async.bulk.tensor.4d.global.shared::cta.bulk_group [%0, {%2, %3, %4, %5}], [%1];" ::"l"(&maps.ts), "r"(sb + OFF_XB + w * 4096),
                       "r"(32 * rank), "r"(0), "r"(2 * q4), "r"(4 * rb + w) : "memory");
          bulk_done_signal(&ws->cntT[32 * q4]);
          asm volatile("mbarrier.arrive.shared::cluster.b64 _, [%0];" ::"r"(mapa(bars + 8 * B_RD0, rank ^ 1)) : "memory");
        }
        __syncwarp();
        if (j == 0) {
          hint_wait(&ws->cntH[0], (ep + 1) * 8u);
          const uint32_t t0 = (uint32_t)clock();
          float2 v;
          do { v = ld_x2((const float2*)ws->Ts + 2 * rb * 64 + t); spin_guard(t0); } while (__any_sync(0xffffffffu, (__float_as_uint(v.y) ^ tag) & 1));
          mbar_wait(bars + 8 * B_TL, 0);
          const uint32_t u = __float_as_uint(v.x);
          *(uint16_t*)(smem + OFF_T + t * 128 + ((t & 7) << 4)) = (uint16_t)u;
          *(uint16_t*)(smem + OFF_T + t * 128 + (((t & 7) ^ 1) << 4)) = (uint16_t)(u >> 16);
          asm volatile("fence.proxy.async.shared::cta;" ::: "memory");
          __syncwarp();
          mbar_arrive_if(lane == 0, bars + 8 * B_T);
        }
      }
    }
  } else {
    asm volatile("setmaxnreg.dec.sync.aligned.u32 24;");
    auto xf_load = [&](int q) {
      const uint32_t fb = bars + 8 * (B_FX + q);
      mbar_expect_tx(fb, U + 8192);
      tma5d(sb + q * U, &maps.x, fb, 64 * q, 2 * rb);
      if (q >= 4) mbar_wait(bars + 8 * (B_FE + ((q - 4) >> 1)), 0);
      tma2d(sb + OFF_XB + (q & 3) * 8192, &maps.ft, fb, 64 * q, 64 * j);
    };
    if (elect_one()) {
      if (warp == 14) {
#pragma unroll
        for (int i = 0; i < B_FT; i++) mbar_init(bars + 8 * i, 1);
        asm volatile("fence.mbarrier_init.release.cluster;" ::: "memory");
        if (!helper) {
#pragma unroll 1
          for (int n = 0; n < 2; n++) {
            const uint32_t fb = bars + 8 * (B_FA + n);
            xf_load(2 * n); xf_load(2 * n + 1);
            mbar_expect_tx(fb, U);
            tma2d(sb + OFF_RING + n * U, &maps.g64, fb, f_full, 64 * n);
            tma2d(sb + OFF_RING + n * U + 8192, &maps.u64, fb, f_full, 64 * n);
          }
        }
      } else if (warp == 15) {
#pragma unroll
        for (int i = B_FT; i < NBAR; i++) mbar_init(bars + 8 * i, i < B_EA ? 1 : i < B_T ? 2 : 4);
#pragma unroll
        for (int i = 0; i < 8; i++) mbar_expect_tx(bars + 8 * (B_Z + i), U / 2);
        asm volatile("fence.mbarrier_init.release.cluster;" ::: "memory");
        asm volatile("fence.proxy.async.shared::cta;" ::: "memory");
      }
    }
    __syncwarp();
    asm volatile("bar.arrive 0, 384;" ::: "memory");
    asm volatile("bar.arrive 4, 256;" ::: "memory");
    __syncwarp();
    asm volatile("barrier.cluster.arrive.relaxed.aligned;" ::: "memory");
    asm volatile("bar.sync 3, 128;" ::: "memory");
    if (warp == 15 && !helper) {
        mbar_wait(bars + 8 * B_FE, 0);
        const uint32_t tag = (ld_x1(&ws->epoch[blockIdx.x * 8]) + 1) & 1;
        const int c = lane >> 4, jj = 16 * blockIdx.x + (lane & 15), jm = (2048 - jj) & 2047;
        const unsigned short* pr = (const unsigned short*)w_r + 256 * c;
        const unsigned short* pi = (const unsigned short*)w_i + 256 * c;
        const float wr = 0.25f * (bf_lo(__ldg(pr + jj * 257)) + bf_lo(__ldg(pr + jm * 257)));
        const float wi = 0.25f * (bf_lo(__ldg(pi + jj * 257)) - bf_lo(__ldg(pi + jm * 257)));
        st_u2(ws->Wh + c * 2048 + jj, c ? pack_bf16(-wi, wr) : pack_bf16(wr, wi), tag);
        __syncwarp();
        hint_add_if(lane == 0, &ws->cntW[0]);
        mbar_wait(bars + 8 * B_XS, 0);
        const uint32_t t0 = (uint32_t)clock();
        uint4 v;
        do { v = ld_x4(ws->gate + rb * 128 + 4 * lane); spin_guard(t0); } while (__any_sync(0xffffffffu, ((v.x ^ tag) | (v.y ^ tag) | (v.z ^ tag) | (v.w ^ tag)) & 1));
        *(uint4*)(smem + OFF_G + lane * 16) = v;
        __syncwarp();
        mbar_arrive_if(lane < 4, bars + 8 * B_G);
      }
    auto part_load = [&](int i, unsigned ep1) {
      const uint32_t bytes = i < 2 ? U : U / 2;
      mbar_wait(bars + 8 * (B_PZ + (i == 0)), 0);
      mbar_expect_tx(bars + 8 * (B_HP + i), bytes);
      flag_wait(&ws->cntP[32 * (rb * 8 + j) + 8 * i], ep1 * (i < 2 ? 8u : 4u));
      bulk_load(sb + (i == 0 ? OFF_T : i == 1 ? 0 : i * (U / 2)), ws->part + (size_t)(rb * 8 + j) * 3072 + (i < 2 ? i * 1024 : 1024 + i * 512), bytes, bars + 8 * (B_HP + i));
    };
    if ((!helper || warp == 15) && elect_one()) {
      if (warp < 14) {
        const int p = warp - 12;
#pragma unroll 1
        for (int i = 4 + p; i < 14; i += 2) asm volatile("prefetch.tensormap [%0];" ::"l"((const char*)&maps + i * 128) : "memory");
#pragma unroll 1
        for (int n = 2; n < 30; n++) {
          const bool table = n == 4 || n == 29;
          const bool half = n >= 17 && n < 21;
          const int q = n < 4 ? n : n < 17 ? n - 1 : n - 5;
          const CUtensorMap* m = table ? &maps.e : half ? &maps.g32 + p : &maps.g64 + p;
          const int c0 = table ? 0 : half ? f_half : f_full + 64 * (q >> 3);
          const int c1 = table ? (n & 1) * 2048 + (2 * rb + p) * 64 : half ? 128 * (n - 17) : 64 * (q & 7);
          const uint32_t fb = bars + 8 * (B_FA + (n & 3)), dst = sb + OFF_RING + (n & 3) * U + p * 8192;
          if (n < 4) mbar_wait(bars + 8 * (B_FE + n - 2), 0);
          else mbar_wait(bars + 8 * (B_EA + (n & 3)), ((n >> 2) & 1) ^ 1);
          tma2d(dst, m, fb, c0, c1);
          if (p == 0) mbar_expect_tx(fb, U);
        }
        part_load(2 + p, ld_x1(&ws->epoch[blockIdx.x * 8]) + 1);
      } else if (warp == 15) {
        const unsigned ep1 = ld_x1(&ws->epoch[blockIdx.x * 8]) + 1;
        flag_wait(&ws->cntX[helper ? 0 : 32 * j], ep1 * 16u);
        mbar_expect_tx(bars + 8 * B_HX, U);
        bulk_load(sb + OFF_XB, ws->X + (size_t)(helper ? 128 : 16 * j + rb) * 8192, U, bars + 8 * B_HX);
        if (!helper) {
          flag_wait(&ws->cntT[32 * q4], ep1 * 128u);
          mbar_expect_tx(bars + 8 * B_TL, U);
          tma3d(sb + OFF_T, &maps.t, bars + 8 * B_TL, 64 * j, 0, 2 * rb);
          part_load(0, ep1); part_load(1, ep1);
          mbar_wait(bars + 8 * (B_HP + 2), 0); mbar_wait(bars + 8 * (B_HP + 3), 0);
          ws->epoch[blockIdx.x * 8] = ep1;
        }
      } else {
#pragma unroll 1
        for (int q = 4; q < 8; q++) xf_load(q);
#pragma unroll 1
        for (int h2 = 0; h2 < 2; h2++) {
          const int s0 = 2 * rb + h2, sg = (s0 & ~6) | ((s0 & 2) << 1) | ((s0 & 4) >> 1);
          mbar_wait(bars + 8 * (B_XS + h2), 0);
#pragma unroll 1
          for (int c = 0; c < 2; c++) {
            asm volatile("cp.async.bulk.tensor.4d.global.shared::cta.bulk_group [%0, {%2, %3, %4, %5}], [%1];" ::"l"(&maps.xs),
                         "r"(sb + OFF_XB + h2 * 8192 + c * 4096), "r"(0), "r"(sg), "r"(0), "r"(16 * j + 8 * c) : "memory");
            if (j == 0)
              asm volatile("cp.async.bulk.global.shared::cta.bulk_group [%0], [%1], 256;" ::"l"(ws->X + 128 * 8192 + c * 4096 + sg * 128),
                           "r"(sb + OFF_SP + h2 * 512 + c * 256) : "memory");
            if (SPACE && h2 + c < 2) __nanosleep(SPACE);
          }
        }
        bulk_done_signal(&ws->cntX[32 * j]);
#pragma unroll 1
        for (int t = 0; t < 8; t++) {
          const int col = 64 * (((q4 + 1 + (t >> 1)) & 3) + 4 * ((t & 1) ? rank : 1 - rank));
          const uint32_t fb = bars + 8 * (B_FT + (t & 3)), dst = sb + (t & 3) * TB;
          mbar_wait(bars + 8 * (B_ET + (t < 3 ? t + 1 : t & 3)), t >> 2);
          mbar_expect_tx(fb, (t & 1) ? 28672 : TB);
          tma2d(dst, &maps.d224, fb, col, 224 * j);
          if (!(t & 1)) tma3d(dst + 28672, &maps.fg, fb, col ^ 256, 16 * rank, 4 * q4);
        }
      }
    }
  }
}

typedef CUresult (*EncodeFn)(CUtensorMap*, CUtensorMapDataType, cuuint32_t, void*, const cuuint64_t*, const cuuint64_t*, const cuuint32_t*,
                             const cuuint32_t*, CUtensorMapInterleave, CUtensorMapSwizzle, CUtensorMapL2promotion, CUtensorMapFloatOOBfill);

static void encode(EncodeFn f, CUtensorMap* m, const void* base, int rank, const cuuint64_t* dims, const cuuint64_t* strides, const cuuint32_t* box,
                   CUtensorMapSwizzle sw) {
  cuuint32_t es[5] = {1, 1, 1, 1, 1};
  f(m, CU_TENSOR_MAP_DATA_TYPE_BFLOAT16, rank, (void*)base, dims, strides, box, es, CU_TENSOR_MAP_INTERLEAVE_NONE, sw,
    CU_TENSOR_MAP_L2_PROMOTION_L2_128B, CU_TENSOR_MAP_FLOAT_OOB_FILL_NONE);
}

extern "C" void kernel_launch(void* const* d_in, const int* in_sizes, int n_in, void* d_out, int out_size) {
  (void)in_sizes; (void)n_in; (void)out_size;
  const __nv_bfloat16* x = (const __nv_bfloat16*)d_in[0];
  const __nv_bfloat16* w_r = (const __nv_bfloat16*)d_in[1];
  const __nv_bfloat16* w_i = (const __nv_bfloat16*)d_in[2];
  const __nv_bfloat16* Wg = (const __nv_bfloat16*)d_in[4];
  const __nv_bfloat16* Wu = (const __nv_bfloat16*)d_in[5];
  const __nv_bfloat16* Wd = (const __nv_bfloat16*)d_in[6];
  const __nv_bfloat16* gw = (const __nv_bfloat16*)d_in[7];

  void* fp = nullptr; cudaDriverEntryPointQueryResult qr;
  cudaGetDriverEntryPoint("cuTensorMapEncodeTiled", &fp, cudaEnableDefault, &qr);
  EncodeFn enc = (EncodeFn)fp;
  void *pFT, *pET, *pDT, *pW;
  cudaGetSymbolAddress(&pDT, g_DT); cudaGetSymbolAddress(&pW, g_work);
  void *pX = ((Work*)pW)->X, *pT = ((Work*)pW)->T;
  cudaGetSymbolAddress(&pFT, g_FT); cudaGetSymbolAddress(&pET, g_ET);

  Maps mp;
  const CUtensorMapSwizzle S128 = CU_TENSOR_MAP_SWIZZLE_128B, S64 = CU_TENSOR_MAP_SWIZZLE_64B;
  { cuuint64_t d[5] = {512, 8, 2, 4, 32}, s[4] = {32768, 1048576, 262144, 1024}; cuuint32_t b[5] = {64, 8, 2, 4, 2}; encode(enc, &mp.x, x, 5, d, s, b, S128); }
  { cuuint64_t d[2] = {512, 512}, s[1] = {1024}; cuuint32_t b[2] = {64, 64}; encode(enc, &mp.ft, pFT, 2, d, s, b, S128); }
  { cuuint64_t d[4] = {128, 32, 2, 129}, s[3] = {256, 8192, 16384}; cuuint32_t b[4] = {128, 1, 2, 8}; encode(enc, &mp.xs, pX, 4, d, s, b, CU_TENSOR_MAP_SWIZZLE_NONE); }
  { cuuint64_t d[4] = {64, 32, 8, 64}, s[3] = {65536, 128, 1024}; cuuint32_t b[4] = {32, 32, 2, 1}; encode(enc, &mp.ts, pT, 4, d, s, b, S64); }
  { cuuint64_t d[3] = {512, 32, 16}, s[2] = {1024, 32768}; cuuint32_t b[3] = {64, 16, 4}; encode(enc, &mp.fg, pFT, 3, d, s, b, S128); }
  { cuuint64_t d[3] = {512, 64, 32}, s[2] = {1024, 65536}; cuuint32_t b[3] = {64, 64, 2}; encode(enc, &mp.t, pT, 3, d, s, b, S128); }
  { cuuint64_t d[2] = {64, 4096}, s[1] = {128}; cuuint32_t b[2] = {64, 64}; encode(enc, &mp.e, pET, 2, d, s, b, S128); }
  { cuuint64_t d[2] = {1792, 512}, s[1] = {3584}; cuuint32_t b[2] = {64, 64}, b2[2] = {32, 128};
    encode(enc, &mp.g64, Wg, 2, d, s, b, S128); encode(enc, &mp.u64, Wu, 2, d, s, b, S128);
    encode(enc, &mp.g32, Wg, 2, d, s, b2, S64); encode(enc, &mp.u32, Wu, 2, d, s, b2, S64); }
  { cuuint64_t d[2] = {512, 1792}, s[1] = {1024}; cuuint32_t b[2] = {64, 224}; encode(enc, &mp.d224, Wd, 2, d, s, b, S128); }
  { cuuint64_t d[4] = {264, 32, 8, 8}, s[3] = {32896, 512, 4112}; cuuint32_t b[4] = {48, 32, 1, 1};
    encode(enc, &mp.wr, w_r, 4, d, s, b, CU_TENSOR_MAP_SWIZZLE_NONE); encode(enc, &mp.wi, w_i, 4, d, s, b, CU_TENSOR_MAP_SWIZZLE_NONE); }

  cudaFuncSetAttribute(fused_kernel, cudaFuncAttributeMaxDynamicSharedMemorySize, SMEM_BYTES);
  fused_kernel<<<NCTA, 512, SMEM_BYTES>>>((Work*)pW, (const uint16_t*)pDT, w_r, w_i, gw, x, (__nv_bfloat16*)d_out, mp);
}
```
